```python
import torch

def _softmax(x, axis=-1):
    return torch.softmax(x, dim=axis)
def _gelu(x):
    return torch.nn.functional.gelu(x, approximate="tanh")
def _silu(x):
    return torch.nn.functional.silu(x)
def _sigmoid(x):
    return torch.sigmoid(x)
def _layernorm(x, axis=-1, eps=1e-5):
    m = x.mean(dim=axis, keepdim=True)
    v = x.var(dim=axis, keepdim=True, unbiased=False)
    return (x - m) / torch.sqrt(v + eps)
def _scatter_add(tgt, idx, src, axis=0):
    return tgt.clone().index_add_(axis, idx, src)
def _segment_sum(src, seg, n):
    out = torch.zeros((n,) + src.shape[1:], dtype=src.dtype)
    return out.index_add_(0, seg, src)
def _pad(x, pw):
    flat = tuple(v for pair in reversed(pw) for v in pair)
    return torch.nn.functional.pad(x, flat)

kernel_name = 'interleave_layers__sliding_local_dilated__linear_kernel_hedgehog__prompt'

def setup_inputs():

    _w = (lambda a: (lambda t: t.to(torch.bfloat16) if t.is_floating_point() else t)(torch.as_tensor(a)))
    def _A_setup():
        B, S, D = 1, 2048, 1024
        return {
            "x": _w((lambda *s: torch.randn(*s, dtype=torch.bfloat16) * 0.05)(B, S, D)),
            "wqkv": _w((lambda *s: torch.randn(*s, dtype=torch.bfloat16) * 0.05)(D, 3 * D)),
            "wo": _w((lambda *s: torch.randn(*s, dtype=torch.bfloat16) * 0.05)(D, D)),
        }
    _A_in = _A_setup()

    def _B_setup():
        B, S, D, H = 1, 2048, 1024, 32
        Dh = D // H
        return {
            "x": _w((lambda *s: torch.randn(*s, dtype=torch.bfloat16) * 0.05)(B, S, D)),
            "wqkv": _w((lambda *s: torch.randn(*s, dtype=torch.bfloat16) * 0.4)(D, 3 * D)),
            "w_phi": _w((lambda *s: torch.randn(*s, dtype=torch.bfloat16) * 0.4)(H, Dh, Dh) * (Dh ** -0.5)),
            "wo": _w((lambda *s: torch.randn(*s, dtype=torch.bfloat16) * 0.1)(D, D)),
        }
    _B_in = _B_setup()

    return {
        "A_x": _A_in["x"],
        "A_wqkv": _A_in["wqkv"],
        "A_wo": _A_in["wo"],
        "B_x": _B_in["x"],
        "B_wqkv": _B_in["wqkv"],
        "B_w_phi": _B_in["w_phi"],
        "B_wo": _B_in["wo"],
    }

def reference(A_x, A_wqkv, A_wo, B_x, B_wqkv, B_w_phi, B_wo):
    def _A_ref(x, wqkv, wo):
        B, S, D = x.shape
        H = 32; Dh = D // H
        W, dil = 8, 2
        qkv = (lambda x, *d: x.permute(*d))((x @ wqkv).reshape(B, S, 3, H, Dh), 2, 0, 3, 1, 4)
        q, k, v = qkv[0], qkv[1], qkv[2]
        scale = Dh ** -0.5
        pos = torch.arange(S)
        off = torch.arange(W) * dil
        idx = pos[:, None] - off[None, :]
        mask = idx >= 0
        idx_c = torch.where(mask, idx, 0).reshape(-1)
        kg = k[:, :, idx_c, :].reshape(B, H, S, W, Dh)
        vg = v[:, :, idx_c, :].reshape(B, H, S, W, Dh)
        logits = torch.einsum("bhsd,bhswd->bhsw", q, kg) * scale
        logits = torch.where(mask[None, None, :, :], logits, -1e9)
        attn = _softmax(logits, axis=-1)
        o = torch.einsum("bhsw,bhswd->bhsd", attn, vg)
        return (lambda x, *d: x.permute(*d))(o, 0, 2, 1, 3).reshape(B, S, D) @ wo

    def _B_ref(x, wqkv, w_phi, wo):
        B, S, D = x.shape
        H = 32; Dh = D // H
        qkv = (lambda x, *d: x.permute(*d))((x @ wqkv).reshape(B, S, 3, H, Dh), 2, 0, 3, 1, 4)
        q, k, v = qkv[0], qkv[1], qkv[2]
        pq = torch.einsum("bhsd,hdf->bhsf", q, w_phi)
        pk = torch.einsum("bhsd,hdf->bhsf", k, w_phi)
        phi_q = torch.concatenate([_softmax(pq, axis=-1), _softmax(-pq, axis=-1)], axis=-1)
        phi_k = torch.concatenate([_softmax(pk, axis=-1), _softmax(-pk, axis=-1)], axis=-1)
        kv = torch.einsum("bhsf,bhsd->bhfd", phi_k, v)
        z  = torch.einsum("bhsf->bhf", phi_k)
        num = torch.einsum("bhqf,bhfd->bhqd", phi_q, kv)
        den = torch.einsum("bhqf,bhf->bhq", phi_q, z)[..., None] + 1e-6
        o = num / den
        return (lambda x, *d: x.permute(*d))(o, 0, 2, 1, 3).reshape(B, S, D) @ wo

    x = A_x
    x = x + _A_ref(_layernorm(x, axis=-1), A_wqkv, A_wo)
    x = x + _B_ref(_layernorm(x, axis=-1), B_wqkv, B_w_phi, B_wo)
    x = x + _A_ref(_layernorm(x, axis=-1), A_wqkv, A_wo)
    x = x + _B_ref(_layernorm(x, axis=-1), B_wqkv, B_w_phi, B_wo)
    return x
```

```cpp
#include <cuda_runtime.h>
#include <cuda.h>
#include <cuda_bf16.h>
#include <stdint.h>

#define NLAYERS 4

namespace {

constexpr int S_LEN = 2048, D_MODEL = 1024;
constexpr int NAUX = 4, NMAIN = 128;
constexpr int SLOT = 16384;
constexpr int OFF_X = 12 * SLOT;
constexpr int OFF_BAR = 14 * SLOT;
constexpr int OFF_ONES = OFF_BAR + 384;
constexpr int OFF_ST = OFF_BAR + 512;
constexpr int OFF_CS = OFF_ST + 1024;
constexpr int SMEM_BYTES = OFF_CS + 1536;
constexpr unsigned long long WO_ASLOT = 0x8762108762108762ull;
constexpr unsigned long long WO_BSLOT = 0xA9B543A9B543A9B5ull;
constexpr int KVH = 9 * 64 * 4;

struct Flags {
  unsigned xready[4][16];
  unsigned oready[4][16];
  unsigned kvready[2][8];
  unsigned csready[8];
  unsigned wfready;
  unsigned done;
  unsigned epoch;
  unsigned error;
};

__device__ Flags g_flags;
__device__ __nv_bfloat16 g_obuf[S_LEN * D_MODEL];
__device__ __nv_bfloat16 g_wfold[D_MODEL * 2048];
__device__ uint4 g_halo[16 * 8 * 1024];
__device__ float g_kv[2][2][32 * KVH];
__device__ float g_colsumA[2][3072];
__device__ float g_colsumB[3072];
__device__ uint4 g_stats[S_LEN * 8];

#define PROFT(i) do {} while (0)
#define PROF(i) do {} while (0)

__device__ __forceinline__ uint32_t smem_u32(const void* p) { return (uint32_t)__cvta_generic_to_shared(p); }
__device__ __forceinline__ bool elect_one() {
  uint32_t p;
  asm volatile("{\n.reg .pred p;\nelect.sync _|p, 0xffffffff;\nselp.u32 %0, 1, 0, p;\n}\n" : "=r"(p));
  return p != 0;
}
__device__ __forceinline__ void mbar_init(uint32_t bar, uint32_t cnt) {
  asm volatile("mbarrier.init.shared::cta.b64 [%0], %1;" :: "r"(bar), "r"(cnt));
}
__device__ __forceinline__ void mbar_expect_tx(uint32_t bar, uint32_t bytes) {
  asm volatile("mbarrier.arrive.expect_tx.shared::cta.b64 _, [%0], %1;" :: "r"(bar), "r"(bytes) : "memory");
}
__device__ __forceinline__ void mbar_wait(uint32_t bar, uint32_t parity) {
  uint32_t ok;
  int it = 0;
  do {
    asm volatile("{\n.reg .pred p;\nmbarrier.try_wait.parity.shared::cta.b64 p, [%1], %2;\nselp.u32 %0, 1, 0, p;\n}\n"
                 : "=r"(ok) : "r"(bar), "r"(parity) : "memory");
  } while (!ok && ++it < (1 << 20));
}
__device__ __forceinline__ void mbar_arrive_local(uint32_t bar) {
  asm volatile("mbarrier.arrive.shared::cta.b64 _, [%0];" :: "r"(bar) : "memory");
}
__device__ __forceinline__ void mbar_arrive_remote(uint32_t bar, uint32_t cta_rank) {
  asm volatile("{\n.reg .b32 ra;\nmapa.shared::cluster.u32 ra, %0, %1;\nmbarrier.arrive.shared::cluster.b64 _, [ra];\n}\n"
               :: "r"(bar), "r"(cta_rank) : "memory");
}
__device__ __forceinline__ void tma_load_2d(uint32_t dst, const CUtensorMap* tm, uint32_t bar, int c0, int c1) {
  asm volatile("cp.async.bulk.tensor.2d.shared::cluster.global.mbarrier::complete_tx::bytes [%0], [%1, {%3, %4}], [%2];"
               :: "r"(dst), "l"(tm), "r"(bar), "r"(c0), "r"(c1) : "memory");
}
__device__ __forceinline__ void tma_load_2d_mc(uint32_t dst, const CUtensorMap* tm, uint32_t bar, int c0, int c1) {
  asm volatile("cp.async.bulk.tensor.2d.shared::cluster.global.mbarrier::complete_tx::bytes.multicast::cluster [%0], [%1, {%3, %4}], [%2], %5;"
               :: "r"(dst), "l"(tm), "r"(bar), "r"(c0), "r"(c1), "h"((uint16_t)3) : "memory");
}
__device__ __forceinline__ void tma_store_2d(const CUtensorMap* tm, uint32_t src, int c0, int c1) {
  asm volatile("cp.async.bulk.tensor.2d.global.shared::cta.bulk_group [%0, {%2, %3}], [%1];"
               :: "l"(tm), "r"(src), "r"(c0), "r"(c1) : "memory");
}
__device__ __forceinline__ void bulk_commit_wait() {
  asm volatile("cp.async.bulk.commit_group;\ncp.async.bulk.wait_group 0;" ::: "memory");
}
__device__ __forceinline__ void prefetch_l2(const void* p, uint32_t bytes) {
  asm volatile("cp.async.bulk.prefetch.L2.global [%0], %1;" :: "l"(p), "r"(bytes) : "memory");
}
__device__ __forceinline__ void prefetch_tmap(const CUtensorMap* tm) {
  asm volatile("prefetch.tensormap [%0];" :: "l"(tm) : "memory");
}
__device__ __forceinline__ void fence_proxy_async_global() { asm volatile("fence.proxy.async.global;" ::: "memory"); }
__device__ __forceinline__ void fence_proxy_async_smem() { asm volatile("fence.proxy.async.shared::cta;" ::: "memory"); }
__device__ __forceinline__ void wait_flag(const unsigned* p, unsigned target) {
  unsigned v;
  int it = 0;
  do {
    asm volatile("ld.acquire.gpu.global.u32 %0, [%1];" : "=r"(v) : "l"(p) : "memory");
  } while ((int)(v - target) < 0 && ++it < (1 << 20));
}
__device__ __forceinline__ void signal_release(unsigned* p) {
  asm volatile("red.release.gpu.global.add.u32 [%0], 1;" :: "l"(p) : "memory");
}
__device__ __forceinline__ void signal_relaxed(unsigned* p) {
  asm volatile("red.relaxed.gpu.global.add.u32 [%0], 1;" :: "l"(p) : "memory");
}
template <int ID, int N> __device__ __forceinline__ void bar_arrive() { asm volatile("bar.arrive %0, %1;" :: "n"(ID), "n"(N) : "memory"); }
template <int ID, int N> __device__ __forceinline__ void bar_sync() { asm volatile("bar.sync %0, %1;" :: "n"(ID), "n"(N) : "memory"); }
__device__ __forceinline__ void bar_wg(int wg) { asm volatile("bar.sync %0, 128;" :: "r"(2 + wg) : "memory"); }
__device__ __forceinline__ void cluster_sync() {
  asm volatile("barrier.cluster.arrive.release.aligned;\nbarrier.cluster.wait.acquire.aligned;" ::: "memory");
}
__device__ __forceinline__ void cluster_wait() { asm volatile("barrier.cluster.wait.acquire.aligned;" ::: "memory"); }
enum { BAR_CONS = 1, BAR_HSEND = 4, BAR_HRECV = 5, BAR_KV = 6, BAR_O = 7, BAR_X = 8, BAR_MID = 9, BAR_HSEND2 = 10 };

__device__ __forceinline__ void wgmma_fence() { asm volatile("wgmma.fence.sync.aligned;" ::: "memory"); }
__device__ __forceinline__ void wgmma_commit() { asm volatile("wgmma.commit_group.sync.aligned;" ::: "memory"); }
template <int N> __device__ __forceinline__ void wgmma_wait() { asm volatile("wgmma.wait_group.sync.aligned %0;" :: "n"(N) : "memory"); }

#define ACC64_OUT(d) \
  "+f"(d[0]), "+f"(d[1]), "+f"(d[2]), "+f"(d[3]), "+f"(d[4]), "+f"(d[5]), "+f"(d[6]), "+f"(d[7]), \
  "+f"(d[8]), "+f"(d[9]), "+f"(d[10]), "+f"(d[11]), "+f"(d[12]), "+f"(d[13]), "+f"(d[14]), "+f"(d[15]), \
  "+f"(d[16]), "+f"(d[17]), "+f"(d[18]), "+f"(d[19]), "+f"(d[20]), "+f"(d[21]), "+f"(d[22]), "+f"(d[23]), \
  "+f"(d[24]), "+f"(d[25]), "+f"(d[26]), "+f"(d[27]), "+f"(d[28]), "+f"(d[29]), "+f"(d[30]), "+f"(d[31]), \
  "+f"(d[32]), "+f"(d[33]), "+f"(d[34]), "+f"(d[35]), "+f"(d[36]), "+f"(d[37]), "+f"(d[38]), "+f"(d[39]), \
  "+f"(d[40]), "+f"(d[41]), "+f"(d[42]), "+f"(d[43]), "+f"(d[44]), "+f"(d[45]), "+f"(d[46]), "+f"(d[47]), \
  "+f"(d[48]), "+f"(d[49]), "+f"(d[50]), "+f"(d[51]), "+f"(d[52]), "+f"(d[53]), "+f"(d[54]), "+f"(d[55]), \
  "+f"(d[56]), "+f"(d[57]), "+f"(d[58]), "+f"(d[59]), "+f"(d[60]), "+f"(d[61]), "+f"(d[62]), "+f"(d[63])
#define ACC64_REGS \
  "{%0,%1,%2,%3,%4,%5,%6,%7,%8,%9,%10,%11,%12,%13,%14,%15,%16,%17,%18,%19,%20,%21,%22,%23,%24,%25,%26,%27,%28,%29,%30,%31," \
  "%32,%33,%34,%35,%36,%37,%38,%39,%40,%41,%42,%43,%44,%45,%46,%47,%48,%49,%50,%51,%52,%53,%54,%55,%56,%57,%58,%59,%60,%61,%62,%63}"

template <int scale_d> __device__ __forceinline__ void wgmma_n128(float (&d)[64], uint64_t descA, uint64_t descB) {
  asm volatile("{\n.reg .pred p;\nsetp.ne.b32 p, %66, 0;\n"
               "wgmma.mma_async.sync.aligned.m64n128k16.f32.bf16.bf16 " ACC64_REGS ", %64, %65, p, 1, 1, 0, 1;\n}\n"
               : ACC64_OUT(d) : "l"(descA), "l"(descB), "n"(scale_d));
}
template <int scale_d> __device__ __forceinline__ void wgmma_n32_tt(float (&d)[16], uint64_t descA, uint64_t descB) {
  asm volatile("{\n.reg .pred p;\nsetp.ne.b32 p, %18, 0;\n"
               "wgmma.mma_async.sync.aligned.m64n32k16.f32.bf16.bf16 {%0,%1,%2,%3,%4,%5,%6,%7,%8,%9,%10,%11,%12,%13,%14,%15}, %16, %17, p, 1, 1, 1, 1;\n}\n"
               : "+f"(d[0]), "+f"(d[1]), "+f"(d[2]), "+f"(d[3]), "+f"(d[4]), "+f"(d[5]), "+f"(d[6]), "+f"(d[7]),
                 "+f"(d[8]), "+f"(d[9]), "+f"(d[10]), "+f"(d[11]), "+f"(d[12]), "+f"(d[13]), "+f"(d[14]), "+f"(d[15])
               : "l"(descA), "l"(descB), "n"(scale_d));
}
template <int scale_d> __device__ __forceinline__ void wgmma_n8_tt(float (&d)[4], uint64_t descA, uint64_t descB) {
  asm volatile("{\n.reg .pred p;\nsetp.ne.b32 p, %6, 0;\n"
               "wgmma.mma_async.sync.aligned.m64n8k16.f32.bf16.bf16 {%0,%1,%2,%3}, %4, %5, p, 1, 1, 1, 1;\n}\n"
               : "+f"(d[0]), "+f"(d[1]), "+f"(d[2]), "+f"(d[3]) : "l"(descA), "l"(descB), "n"(scale_d));
}
template <int scale_d> __device__ __forceinline__ void wgmma_n40(float (&d)[20], uint64_t descA, uint64_t descB) {
  asm volatile("{\n.reg .pred p;\nsetp.ne.b32 p, %22, 0;\n"
               "wgmma.mma_async.sync.aligned.m64n40k16.f32.bf16.bf16 {%0,%1,%2,%3,%4,%5,%6,%7,%8,%9,%10,%11,%12,%13,%14,%15,%16,%17,%18,%19}, %20, %21, p, 1, 1, 0, 1;\n}\n"
               : "+f"(d[0]), "+f"(d[1]), "+f"(d[2]), "+f"(d[3]), "+f"(d[4]), "+f"(d[5]), "+f"(d[6]), "+f"(d[7]),
                 "+f"(d[8]), "+f"(d[9]), "+f"(d[10]), "+f"(d[11]), "+f"(d[12]), "+f"(d[13]), "+f"(d[14]), "+f"(d[15]),
                 "+f"(d[16]), "+f"(d[17]), "+f"(d[18]), "+f"(d[19])
               : "l"(descA), "l"(descB), "n"(scale_d));
}
__device__ __forceinline__ uint64_t make_desc(uint32_t addr, uint32_t lbo_bytes, uint32_t sbo_bytes) {
  return (uint64_t)((addr & 0x3FFFF) >> 4) | ((uint64_t)(lbo_bytes >> 4) << 16) | ((uint64_t)(sbo_bytes >> 4) << 32) | (1ull << 62);
}

__device__ __forceinline__ void ldsm_x4(uint32_t addr, uint32_t& r0, uint32_t& r1, uint32_t& r2, uint32_t& r3) {
  asm volatile("ldmatrix.sync.aligned.m8n8.x4.shared.b16 {%0,%1,%2,%3}, [%4];" : "=r"(r0), "=r"(r1), "=r"(r2), "=r"(r3) : "r"(addr) : "memory");
}
__device__ __forceinline__ void ldsm_x4_t(uint32_t addr, uint32_t& r0, uint32_t& r1, uint32_t& r2, uint32_t& r3) {
  asm volatile("ldmatrix.sync.aligned.m8n8.x4.trans.shared.b16 {%0,%1,%2,%3}, [%4];" : "=r"(r0), "=r"(r1), "=r"(r2), "=r"(r3) : "r"(addr) : "memory");
}
__device__ __forceinline__ void stsm_x4(uint32_t addr, uint32_t r0, uint32_t r1, uint32_t r2, uint32_t r3) {
  asm volatile("stmatrix.sync.aligned.m8n8.x4.shared.b16 [%0], {%1,%2,%3,%4};" :: "r"(addr), "r"(r0), "r"(r1), "r"(r2), "r"(r3) : "memory");
}
__device__ __forceinline__ uint4 lds128(uint32_t addr) {
  uint4 v;
  asm volatile("ld.shared.v4.u32 {%0,%1,%2,%3}, [%4];" : "=r"(v.x), "=r"(v.y), "=r"(v.z), "=r"(v.w) : "r"(addr) : "memory");
  return v;
}
__device__ __forceinline__ void sts128(uint32_t addr, uint32_t a, uint32_t b, uint32_t c, uint32_t d) {
  asm volatile("st.shared.v4.u32 [%0], {%1,%2,%3,%4};" :: "r"(addr), "r"(a), "r"(b), "r"(c), "r"(d) : "memory");
}
__device__ __forceinline__ float2 lds64f(uint32_t addr) {
  float2 v;
  asm volatile("ld.shared.v2.f32 {%0,%1}, [%2];" : "=f"(v.x), "=f"(v.y) : "r"(addr) : "memory");
  return v;
}
__device__ __forceinline__ float4 lds128f(uint32_t addr) {
  float4 v;
  asm volatile("ld.shared.v4.f32 {%0,%1,%2,%3}, [%4];" : "=f"(v.x), "=f"(v.y), "=f"(v.z), "=f"(v.w) : "r"(addr) : "memory");
  return v;
}
__device__ __forceinline__ void mma_bf16(float (&c)[4], uint32_t a0, uint32_t a1, uint32_t a2, uint32_t a3, uint32_t b0, uint32_t b1) {
  asm("mma.sync.aligned.m16n8k16.row.col.f32.bf16.bf16.f32 {%0,%1,%2,%3}, {%4,%5,%6,%7}, {%8,%9}, {%0,%1,%2,%3};"
               : "+f"(c[0]), "+f"(c[1]), "+f"(c[2]), "+f"(c[3]) : "r"(a0), "r"(a1), "r"(a2), "r"(a3), "r"(b0), "r"(b1));
}
__device__ __forceinline__ uint32_t movm_t(uint32_t v) {
  uint32_t r;
  asm volatile("movmatrix.sync.aligned.m8n8.trans.b16 %0, %1;" : "=r"(r) : "r"(v));
  return r;
}
__device__ __forceinline__ uint32_t pack_bf16(float lo, float hi) {
  uint32_t r;
  asm("cvt.rn.bf16x2.f32 %0, %1, %2;" : "=r"(r) : "f"(hi), "f"(lo));
  return r;
}
__device__ __forceinline__ float bf_lo(uint32_t v) { return __uint_as_float(v << 16); }
__device__ __forceinline__ float bf_hi(uint32_t v) { return __uint_as_float(v & 0xFFFF0000u); }
__device__ __forceinline__ float ex2(float x) { float r; asm("ex2.approx.ftz.f32 %0, %1;" : "=f"(r) : "f"(x)); return r; }
__device__ __forceinline__ float rcp_fast(float x) { float r; asm("rcp.approx.ftz.f32 %0, %1;" : "=f"(r) : "f"(x)); return r; }
__device__ __forceinline__ void red_v4(float* p, float a, float b, float c, float d) {
  asm volatile("red.global.add.v4.f32 [%0], {%1, %2, %3, %4};" :: "l"(p), "f"(a), "f"(b), "f"(c), "f"(d) : "memory");
}
__device__ __forceinline__ void red_v2(float* p, float a, float b) {
  asm volatile("red.global.add.v2.f32 [%0], {%1, %2};" :: "l"(p), "f"(a), "f"(b) : "memory");
}
__device__ __forceinline__ void red_f32(float* p, float a) {
  asm volatile("red.global.add.f32 [%0], %1;" :: "l"(p), "f"(a) : "memory");
}

constexpr float LOG2E = 1.4426950408889634f;

struct Params {
  const __nv_bfloat16* wA_qkv;
  const __nv_bfloat16* wA_o;
  const __nv_bfloat16* wB_qkv;
  const __nv_bfloat16* wB_phi;
  const __nv_bfloat16* wB_o;
};

#define ACC_DEF(d, n) _Pragma("unroll") for (int i_ = 0; i_ < (n); i_++) asm volatile("" : "=f"(d[i_]))
#define ACC_FENCE(d, n) _Pragma("unroll") for (int i_ = 0; i_ < (n); i_++) asm volatile("" : "+f"(d[i_]) :: "memory")

#define STAGE_ACC_LN(acc, p0, p1, csa, NB) \
  _Pragma("unroll") for (int b_ = 0; b_ < 8; b_ += (NB)) { \
    float4 c_[NB]; \
    _Pragma("unroll") for (int j_ = 0; j_ < (NB); j_++) c_[j_] = lds128f((csa) + (b_ + j_) * 64); \
    _Pragma("unroll") for (int j_ = b_; j_ < b_ + (NB); j_++) { \
      const float4 c4_ = c_[j_ - b_]; \
      stsm_x4(((j_ < 4) ? (p0) : (p1)) + srowoff + ((((uint32_t)(j_ & 3) << 5) + lhi) ^ lsw), \
              pack_bf16(rs0 * fmaf(nm0, c4_.x, acc[j_ * 8 + 0]), rs0 * fmaf(nm0, c4_.y, acc[j_ * 8 + 1])), \
              pack_bf16(rs1 * fmaf(nm1, c4_.x, acc[j_ * 8 + 2]), rs1 * fmaf(nm1, c4_.y, acc[j_ * 8 + 3])), \
              pack_bf16(rs0 * fmaf(nm0, c4_.z, acc[j_ * 8 + 4]), rs0 * fmaf(nm0, c4_.w, acc[j_ * 8 + 5])), \
              pack_bf16(rs1 * fmaf(nm1, c4_.z, acc[j_ * 8 + 6]), rs1 * fmaf(nm1, c4_.w, acc[j_ * 8 + 7]))); \
    } \
  }
#define PHI_LOAD(acc, off, csa) \
  _Pragma("unroll") for (int j_ = 0; j_ < 4; j_++) { \
    const float4 c_ = lds128f((csa) + j_ * 64); \
    float (&pa_)[4] = p[j_ >> 1][(j_ & 1) * 2]; float (&pb_)[4] = p[j_ >> 1][(j_ & 1) * 2 + 1]; \
    pa_[0] = fmaf(nm0, c_.x, acc[(off) + j_ * 8 + 0]); pa_[1] = fmaf(nm0, c_.y, acc[(off) + j_ * 8 + 1]); \
    pa_[2] = fmaf(nm1, c_.x, acc[(off) + j_ * 8 + 2]); pa_[3] = fmaf(nm1, c_.y, acc[(off) + j_ * 8 + 3]); \
    pb_[0] = fmaf(nm0, c_.z, acc[(off) + j_ * 8 + 4]); pb_[1] = fmaf(nm0, c_.w, acc[(off) + j_ * 8 + 5]); \
    pb_[2] = fmaf(nm1, c_.z, acc[(off) + j_ * 8 + 6]); pb_[3] = fmaf(nm1, c_.w, acc[(off) + j_ * 8 + 7]); \
  }

__global__ void __cluster_dims__(2, 1, 1) __launch_bounds__(384, 1)
mega_kernel(const __grid_constant__ CUtensorMap tm_x0, const __grid_constant__ CUtensorMap tm_xo,
            const __grid_constant__ CUtensorMap tm_o, const __grid_constant__ CUtensorMap tm_wf,
            const __grid_constant__ CUtensorMap tm_wqA, const __grid_constant__ CUtensorMap tm_wqB,
            const __grid_constant__ CUtensorMap tm_woA, const __grid_constant__ CUtensorMap tm_woB, const Params prm) {
  extern __shared__ __align__(1024) uint8_t smem_raw[];
  const uint32_t sbase = smem_u32(smem_raw);
  const uint32_t bar_full = sbase + OFF_BAR;
  const uint32_t bar_done = bar_full + 128;
  const uint32_t bar_stat = bar_full + 256, bar_epi = bar_full + 264, bar_x0 = bar_full + 272;

  const int warp = threadIdx.x >> 5, lane = threadIdx.x & 31;
  uint32_t rank;
  asm volatile("mov.u32 %0, %%cluster_ctarank;" : "=r"(rank));
  const int cta = (int)blockIdx.x - NAUX;
  const int cl = cta >> 1;
  const int jj = cl & 7, cc = cl >> 3;
  const int mm = cc * 2 + (int)rank;

  unsigned epoch;
  asm volatile("ld.relaxed.gpu.global.u32 %0, [%1];" : "=r"(epoch) : "l"(&g_flags.epoch) : "memory");
  const unsigned ep1 = epoch + 1;
  const int par = ep1 & 1;

  if (cta >= 0) {
    if (threadIdx.x == 0) {
      for (int i = 0; i < 16; i++) { mbar_init(bar_full + i * 8, 1); mbar_init(bar_done + i * 8, 16); }
      mbar_init(bar_stat, 2); mbar_init(bar_epi, 16); mbar_init(bar_x0, 1);
      asm volatile("fence.mbarrier_init.release.cluster;" ::: "memory");
    }
    if (warp == 1) asm volatile("st.shared.u32 [%0], %1;" :: "r"(sbase + OFF_ONES + lane * 4), "r"(0x3F803F80u) : "memory");
    __syncthreads();
    asm volatile("barrier.cluster.arrive.release.aligned;" ::: "memory");
  }

  if (cta < 0) {
    const int g = lane >> 2, t = lane & 3;
    const int id = blockIdx.x * 12 + warp, p = id % 3, hp = id / 3;
    const uint32_t buf = sbase + warp * SLOT, bar = sbase + OFF_BAR + warp * 16;
    const uint32_t lsw = (lane & 7) << 4, lhi = (lane >> 4) << 4, lrow = (lane & 15) * 128;
    const bool el = elect_one();
    if (el) {
      mbar_init(bar, 1); mbar_init(bar + 8, 1);
      asm volatile("fence.mbarrier_init.release.cluster;" ::: "memory");
      for (int i = 0; i < 2; i++) { mbar_expect_tx(bar + i * 8, 8192); tma_load_2d(buf + i * 8192, &tm_wqB, bar + i * 8, p * 1024 + hp * 64, i * 64); }
    }
    __syncwarp();
    uint32_t b[2][4][4];
#pragma unroll
    for (int i = 0; i < 32; i++)
      b[i >> 4][(i >> 2) & 3][i & 3] = movm_t(__ldg(reinterpret_cast<const uint32_t*>(prm.wB_phi + (hp * 2) * 1024 + ((i >> 2) * 8 + g) * 32 + (i & 3) * 8) + t));
    float cs[8][4];
#pragma unroll
    for (int i = 0; i < 8; i++) cs[i][0] = cs[i][1] = cs[i][2] = cs[i][3] = 0.f;
#pragma unroll 1
    for (int rc = 0; rc < 16; rc++) {
      const uint32_t tb = buf + (rc & 1) * 8192 + lrow;
      mbar_wait(bar + (rc & 1) * 8, (rc >> 1) & 1);
#pragma unroll 1
      for (int mt = 0; mt < 4; mt++) {
        if (p < 2) {
#pragma unroll
          for (int hh = 0; hh < 2; hh++) {
            uint32_t a[2][4];
#pragma unroll
            for (int ks = 0; ks < 2; ks++) ldsm_x4(tb + mt * 2048 + ((hh * 64 + ks * 32 + lhi) ^ lsw), a[ks][0], a[ks][1], a[ks][2], a[ks][3]);
            float c[4][4];
#pragma unroll
            for (int n = 0; n < 4; n++) {
              c[n][0] = c[n][1] = c[n][2] = c[n][3] = 0.f;
              mma_bf16(c[n], a[0][0], a[0][1], a[0][2], a[0][3], b[hh][0][n], b[hh][1][n]);
              mma_bf16(c[n], a[1][0], a[1][1], a[1][2], a[1][3], b[hh][2][n], b[hh][3][n]);
            }
#pragma unroll
            for (int ks = 0; ks < 2; ks++)
              stsm_x4(tb + mt * 2048 + ((hh * 64 + ks * 32 + lhi) ^ lsw), pack_bf16(c[2 * ks][0], c[2 * ks][1]), pack_bf16(c[2 * ks][2], c[2 * ks][3]),
                      pack_bf16(c[2 * ks + 1][0], c[2 * ks + 1][1]), pack_bf16(c[2 * ks + 1][2], c[2 * ks + 1][3]));
          }
          __syncwarp();
        }
#pragma unroll
        for (int cb = 0; cb < 4; cb++) {
          uint32_t b0, b1, b2, b3;
          ldsm_x4_t(tb + mt * 2048 + ((cb * 32 + lhi) ^ lsw), b0, b1, b2, b3);
          mma_bf16(cs[2 * cb], 0x3F803F80u, 0x3F803F80u, 0x3F803F80u, 0x3F803F80u, b0, b1);
          mma_bf16(cs[2 * cb + 1], 0x3F803F80u, 0x3F803F80u, 0x3F803F80u, 0x3F803F80u, b2, b3);
        }
      }
      fence_proxy_async_smem();
      __syncwarp();
      if (el) {
        if (p < 2) {
          tma_store_2d(&tm_wf, buf + (rc & 1) * 8192, p * 1024 + hp * 64, rc * 64);
          asm volatile("cp.async.bulk.commit_group;\ncp.async.bulk.wait_group.read 0;" ::: "memory");
        }
        if (rc < 14) {
          mbar_expect_tx(bar + (rc & 1) * 8, 8192);
          tma_load_2d(buf + (rc & 1) * 8192, &tm_wqB, bar + (rc & 1) * 8, p * 1024 + hp * 64, (rc + 2) * 64);
        }
      }
      __syncwarp();
    }
    if (g == 0) {
#pragma unroll
      for (int n = 0; n < 8; n++) *reinterpret_cast<float2*>(g_colsumB + p * 1024 + hp * 64 + n * 8 + t * 2) = make_float2(cs[n][0], cs[n][1]);
    }
    if (el) asm volatile("cp.async.bulk.wait_group 0;" ::: "memory");
    __syncthreads();
    if (threadIdx.x == 0) signal_release(&g_flags.wfready);
  } else if (warp >= 8) {
    asm volatile("setmaxnreg.dec.sync.aligned.u32 40;");
    if (warp == 8) {
      const bool el = elect_one();
      if (el) prefetch_tmap(&tm_wqA);
      cluster_wait();
      if (el) {
        const int col = jj * 128 + (int)rank * 64;
#pragma unroll 1
        for (int l = 0; l < NLAYERS; l++) {
          const CUtensorMap* tqk = (l & 1) ? &tm_wf : &tm_wqA;
          const CUtensorMap* tv = (l & 1) ? &tm_wqB : &tm_wqA;
          const CUtensorMap* two = (l & 1) ? &tm_woB : &tm_woA;
          int kk = 2 * jj;
          if (l == 1) { wait_flag(&g_flags.wfready, ep1 * NAUX); fence_proxy_async_global(); }
          uint32_t dst = sbase + rank * 8192;
#pragma unroll 1
          for (int i = 0; i < 16; i++) {
            if (i >= 3) mbar_wait(bar_done + (i - 3) * 8, 0);
            else if (l) mbar_wait(bar_done + (i == 2 ? 15 : 12) * 8, 1);
            const uint32_t fb = bar_full + i * 8;
            mbar_expect_tx(fb, (i < 2) ? 3 * SLOT : 4 * SLOT);
            tma_load_2d_mc(dst, tqk, fb, col, kk * 64);
            tma_load_2d_mc(dst + SLOT, tqk, fb, col + 1024, kk * 64);
            tma_load_2d_mc(dst + 2 * SLOT, tv, fb, col + 2048, kk * 64);
            kk = (kk + 1) & 15;
            dst += 3 * SLOT;
            if (dst >= sbase + 9 * SLOT) dst -= 9 * SLOT;
          }
#pragma unroll 1
          for (int n = 0; n < 16; n++) {
            const int s = (n < 6) ? ((0x325410 >> (4 * n)) & 15) : n;
            if (n >= 6) mbar_wait(bar_done + (n - 6) * 8, 1);
            else if (n == 0) mbar_wait(bar_done + 13 * 8, 0);
            else if (n == 4) mbar_wait(bar_done + 14 * 8, 0);
            else if (n == 5) mbar_wait(bar_epi, l & 1);
            const uint32_t fb = bar_full + s * 8;
            mbar_expect_tx(fb, (s < 2) ? SLOT : 2 * SLOT);
            tma_load_2d_mc(sbase + rank * 8192 + (uint32_t)((WO_BSLOT >> (4 * s)) & 15) * SLOT, two, fb, col, ((2 * jj + s) & 15) * 64);
          }
        }
      }
      __syncwarp();
    } else if (warp == 9) {
      const bool el = elect_one();
      if (el) {
        mbar_expect_tx(bar_x0, 2 * SLOT);
        tma_load_2d(sbase + OFF_X, &tm_x0, bar_x0, jj * 128, mm * 128);
        tma_load_2d(sbase + OFF_X + SLOT, &tm_x0, bar_x0, jj * 128 + 64, mm * 128);
      }
#pragma unroll 1
      for (int l = 0; l < NLAYERS; l++) {
        if (el) {
          const CUtensorMap* tx = l ? &tm_xo : &tm_x0;
          if (l) {
            wait_flag(&g_flags.xready[l][mm], ep1 * 8);
            fence_proxy_async_global();
            PROFT(160 + l * 8);
            mbar_wait(bar_done + 15 * 8, 1);
          }
          uint32_t dst = sbase + 9 * SLOT;
#pragma unroll 1
          for (int i = 2; i < 16; i++) {
            if (i >= 5) mbar_wait(bar_done + (i - 3) * 8, 0);
            tma_load_2d(dst, tx, bar_full + i * 8, ((2 * jj + i) & 15) * 64, mm * 128);
            dst += SLOT;
            if (dst == sbase + 12 * SLOT) dst = sbase + 9 * SLOT;
          }
        }
        __syncwarp();
        if (l == 0) cluster_wait();
        bar_sync<BAR_O, 288>();
        if (el) {
          PROFT(161 + l * 8);
          tma_store_2d(&tm_o, sbase + 2 * SLOT, jj * 128, mm * 128);
          tma_store_2d(&tm_o, sbase + 6 * SLOT, jj * 128 + 64, mm * 128);
          bulk_commit_wait();
          signal_relaxed(&g_flags.oready[l][mm]);
          PROFT(162 + l * 8);
          wait_flag(&g_flags.oready[l][mm], ep1 * 8);
          fence_proxy_async_global();
          PROFT(163 + l * 8);
          mbar_wait(bar_done + 15 * 8, 0);
#pragma unroll 1
          for (int s = 2; s < 16; s++) {
            if (s >= 6) mbar_wait(bar_done + (s - 6) * 8, 1);
            tma_load_2d(sbase + (uint32_t)((WO_ASLOT >> (4 * s)) & 15) * SLOT, &tm_o, bar_full + s * 8, ((2 * jj + s) & 15) * 64, mm * 128);
          }
        }
        __syncwarp();
        bar_sync<BAR_X, 352>();
        if (el) {
          PROFT(164 + l * 8);
          tma_store_2d(&tm_xo, sbase + OFF_X, jj * 128, mm * 128);
          tma_store_2d(&tm_xo, sbase + OFF_X + SLOT, jj * 128 + 64, mm * 128);
          bulk_commit_wait();
          if (l < 3) signal_relaxed(&g_flags.xready[l + 1][mm]);
          PROFT(165 + l * 8);
        }
        __syncwarp();
      }
    } else {
      const int hw = warp - 10, ht = hw * 32 + lane;
      const char* wrow = reinterpret_cast<const char*>(prm.wA_qkv + (size_t)mm * 64 * 3072 + jj * 128);
#pragma unroll
      for (int p = 0; p < 3; p++) prefetch_l2(wrow + (size_t)ht * 6144 + p * 2048, 256);
      cluster_wait();
      const uint32_t sw = (lane & 7) << 4;
      mbar_wait(bar_x0, 0);
#pragma unroll 1
      for (int l = 0; l < NLAYERS; l++) {
        const uint32_t tag = ep1 * 4 + l;
        uint4* srow = g_stats + (size_t)(mm * 128 + hw * 64 + lane) * 8;
#pragma unroll 1
        for (int rr = 0; rr < 2; rr++) {
          const uint32_t a = sbase + OFF_X + (hw * 64 + rr * 32 + lane) * 128;
          uint32_t w0;
          asm volatile("ld.shared.u32 %0, [%1];" : "=r"(w0) : "r"(a) : "memory");
          const float pv = bf_lo(w0);
          float s0 = 0.f, s1 = 0.f, q0 = 0.f, q1 = 0.f;
#pragma unroll 1
          for (int c = 0; c < 16; c += 4) {
            uint4 v[4];
#pragma unroll
            for (int i = 0; i < 4; i++) v[i] = lds128(a + (c >> 3) * SLOT + ((((c & 7) + i) << 4) ^ sw));
#pragma unroll
            for (int i = 0; i < 4; i++) {
              float d;
              d = bf_lo(v[i].x) - pv; s0 += d; q0 = fmaf(d, d, q0); d = bf_hi(v[i].x) - pv; s1 += d; q1 = fmaf(d, d, q1);
              d = bf_lo(v[i].y) - pv; s0 += d; q0 = fmaf(d, d, q0); d = bf_hi(v[i].y) - pv; s1 += d; q1 = fmaf(d, d, q1);
              d = bf_lo(v[i].z) - pv; s0 += d; q0 = fmaf(d, d, q0); d = bf_hi(v[i].z) - pv; s1 += d; q1 = fmaf(d, d, q1);
              d = bf_lo(v[i].w) - pv; s0 += d; q0 = fmaf(d, d, q0); d = bf_hi(v[i].w) - pv; s1 += d; q1 = fmaf(d, d, q1);
            }
          }
          s0 += s1; q0 += q1;
          const float mu = s0 * (1.f / 128.f);
          asm volatile("{\n.reg .b128 v;\nmov.b128 v, {%1, %2, %3, %3};\nst.relaxed.gpu.global.b128 [%0], v;\n}\n"
                       :: "l"(srow + rr * 256 + jj), "f"(pv + mu), "f"(fmaf(-s0, mu, q0)), "r"(tag) : "memory");
        }
        if (l == 0) {
          if (ht < 48) {
            const uint4* wp = reinterpret_cast<const uint4*>(wrow + (ht >> 4) * 2048) + (ht & 15);
            float c0 = 0.f, c1 = 0.f, c2 = 0.f, c3 = 0.f, c4 = 0.f, c5 = 0.f, c6 = 0.f, c7 = 0.f;
#pragma unroll 1
            for (int r = 0; r < 64; r += 4) {
              uint4 v[4];
#pragma unroll
              for (int i = 0; i < 4; i++) v[i] = __ldcg(wp + (r + i) * 384);
#pragma unroll
              for (int i = 0; i < 4; i++) {
                c0 += bf_lo(v[i].x); c1 += bf_hi(v[i].x); c2 += bf_lo(v[i].y); c3 += bf_hi(v[i].y);
                c4 += bf_lo(v[i].z); c5 += bf_hi(v[i].z); c6 += bf_lo(v[i].w); c7 += bf_hi(v[i].w);
              }
            }
            float* d = g_colsumA[par] + (ht >> 4) * 1024 + jj * 128 + (ht & 15) * 8;
            red_v4(d, c0, c1, c2, c3); red_v4(d + 4, c4, c5, c6, c7);
          }
          __syncwarp();
          if (lane == 0) signal_release(&g_flags.csready[jj]);
          if (ht < 16) prefetch_l2((const char*)((ht & 8) ? prm.wB_o : prm.wA_o) + (size_t)cta * 16384 + (ht & 7) * 2048, 2048);
        }
#pragma unroll 1
        for (int rr = 0; rr < 2; rr++) {
          float sm[8], m2 = 0.f;
#pragma unroll
          for (int hf = 0; hf < 2; hf++) {
            uint32_t bad;
            int it = 0;
            float q;
            do {
              bad = 0; q = 0.f;
#pragma unroll
              for (int i = 0; i < 4; i++) {
                float qq; uint32_t tg, dm;
                asm volatile("{\n.reg .b128 v;\nld.relaxed.gpu.global.b128 v, [%4];\nmov.b128 {%0, %1, %2, %3}, v;\n}\n"
                             : "=f"(sm[hf * 4 + i]), "=f"(qq), "=r"(tg), "=r"(dm) : "l"(srow + rr * 256 + hf * 4 + i) : "memory");
                bad |= tg ^ tag; q += qq;
              }
            } while (bad && ++it < (1 << 18));
            m2 += q;
          }
          const float mean = (((sm[0] + sm[1]) + (sm[2] + sm[3])) + ((sm[4] + sm[5]) + (sm[6] + sm[7]))) * 0.125f;
          float dd = 0.f;
#pragma unroll
          for (int i = 0; i < 8; i++) { const float e = sm[i] - mean; dd = fmaf(e, e, dd); }
          const float rs = rsqrtf(fmaxf(fmaf(dd, 128.f, m2), 0.f) * (1.f / 1024.f) + 1e-5f);
          asm volatile("st.shared.v2.f32 [%0], {%1, %2};" :: "r"(sbase + OFF_ST + (hw * 64 + rr * 32 + lane) * 8), "f"(rs), "f"(-mean) : "memory");
        }
        {
          if (l < 2 && lane == 0) wait_flag(l ? &g_flags.wfready : &g_flags.csready[jj], l ? ep1 * NAUX : ep1 * 32);
          __syncwarp();
          const float2* src = reinterpret_cast<const float2*>(((l & 1) ? g_colsumB : g_colsumA[par]) + jj * 128) + ht;
          const uint32_t dst = sbase + OFF_CS + (ht >> 3) * 64 + (ht & 3) * 16 + ((ht >> 2) & 1) * 8;
#pragma unroll
          for (int p = 0; p < 3; p++) {
            const float2 v = __ldcg(src + p * 512);
            asm volatile("st.shared.v2.f32 [%0], {%1, %2};" :: "r"(dst + p * 512), "f"(v.x), "f"(v.y) : "memory");
          }
          __syncwarp();
          if (lane == 0) { mbar_arrive_local(bar_stat); PROFT(192 + l * 2 + hw); }
        }
        if (l == 1) {
          float4* z = reinterpret_cast<float4*>(&g_kv[par ^ 1][0][0]) + cta * (2 * 32 * KVH / 4 / NMAIN);
#pragma unroll 1
          for (int i = ht; i < 2 * 32 * KVH / 4 / NMAIN; i += 64) z[i] = make_float4(0.f, 0.f, 0.f, 0.f);
        }
        if (l == 0 && ht < 24) g_colsumA[par ^ 1][cta * 24 + ht] = 0.f;
        if (l & 1) {
          if (warp == 10) {
            bar_sync<BAR_KV, 288>();
            if (lane == 0) { PROFT(166 + l * 8); signal_release(&g_flags.kvready[l >> 1][jj]); PROFT(167 + l * 8); }
          }
        } else {
          if (hw) bar_sync<BAR_HSEND, 64>(); else bar_sync<BAR_HSEND2, 64>();
          if (mm < 15) {
            uint4* dst = g_halo + (size_t)(mm * 8 + jj) * 1024 + (hw ? 0 : 512) + lane;
            const uint32_t sp = sbase + (hw ? 0 : 7 * SLOT) + 112 * 128 + lane * 8;
#pragma unroll
            for (int pc = 0; pc < 2; pc++) {
              uint32_t d[8][2];
#pragma unroll
              for (int i = 0; i < 8; i++) asm volatile("ld.shared.v2.u32 {%0, %1}, [%2];" : "=r"(d[i][0]), "=r"(d[i][1]) : "r"(sp + pc * SLOT + i * 256) : "memory");
#pragma unroll
              for (int i = 0; i < 8; i++)
                asm volatile("{\n.reg .b64 a, b;\nmov.b64 a, {%1, %3};\nmov.b64 b, {%2, %3};\nst.relaxed.gpu.global.v2.b64 [%0], {a, b};\n}\n"
                             :: "l"(dst + (pc * 8 + i) * 32), "r"(d[i][0]), "r"(d[i][1]), "r"(tag) : "memory");
            }
          }
        }
        __syncwarp();
        bar_sync<BAR_X, 352>();
      }
    }
    cluster_sync();
  } else {
    asm volatile("setmaxnreg.inc.sync.aligned.u32 232;");
    const int tid = threadIdx.x;
    const int wg = warp >> 2;
    const int g = lane >> 2, t = lane & 3;
    const int r0 = warp * 16;
    const uint32_t srowoff = (r0 + (lane & 15)) * 128;
    const uint32_t lsw = (lane & 7) << 4, lhi = (lane >> 4) << 4;
    const uint32_t pK0 = sbase, pK1 = sbase + SLOT, pQ0 = sbase + 2 * SLOT, pQ1 = sbase + 6 * SLOT, pV0 = sbase + 7 * SLOT, pV1 = sbase + 8 * SLOT;
    cluster_wait();
    PROF(0);
    mbar_wait(bar_x0, 0);

#pragma unroll 1
    for (int l = 0; l < NLAYERS; l++) {
      PROF(1 + l * 16);
      float accq[64], acck[64], accv[64];
      ACC_DEF(accq, 64); ACC_DEF(acck, 64); ACC_DEF(accv, 64);
      {
        uint32_t a = sbase + OFF_X + wg * 8192, bst = sbase;
#define QKV_STEP(SC0) { \
          const uint64_t da = make_desc(a, 16, 1024); \
          a += SLOT; if (a >= sbase + 14 * SLOT) a -= 5 * SLOT; else if (i >= 2 && a >= sbase + 12 * SLOT) a -= 3 * SLOT; \
          const uint64_t db = make_desc(bst, 8192, 1024); \
          bst += 3 * SLOT; if (bst == sbase + 9 * SLOT) bst = sbase; \
          mbar_wait(bar_full + i * 8, 0); \
          if (i == 0) PROF(2 + l * 16); \
          if (i == 2) PROF(3 + l * 16); \
          wgmma_fence(); \
          wgmma_n128<SC0>(accq, da, db); wgmma_n128<SC0>(acck, da, db + 1024); wgmma_n128<SC0>(accv, da, db + 2048); \
          _Pragma("unroll") for (int k4 = 1; k4 < 4; k4++) { \
            wgmma_n128<1>(accq, da + k4 * 2, db + k4 * 128); \
            wgmma_n128<1>(acck, da + k4 * 2, db + 1024 + k4 * 128); \
            wgmma_n128<1>(accv, da + k4 * 2, db + 2048 + k4 * 128); \
          } \
          wgmma_commit(); }
        { const int i = 0; QKV_STEP(0) }
#pragma unroll 1
        for (int i = 1; i < 16; i++) {
          QKV_STEP(1)
          wgmma_wait<1>();
          if (lane < 2) mbar_arrive_remote(bar_done + (i - 1) * 8, lane);
        }
        wgmma_wait<0>();
        ACC_FENCE(accq, 64); ACC_FENCE(acck, 64); ACC_FENCE(accv, 64);
        if (lane < 2) mbar_arrive_remote(bar_done + 15 * 8, lane);
      }
      PROF(4 + l * 16);
      mbar_wait(bar_stat, l & 1);
      const float2 st0_ = lds64f(sbase + OFF_ST + (r0 + g) * 8), st1_ = lds64f(sbase + OFF_ST + (r0 + g + 8) * 8);
      const float rs0 = st0_.x, nm0 = st0_.y, rs1 = st1_.x, nm1 = st1_.y;
      const uint32_t csa = sbase + OFF_CS + t * 16;
      mbar_wait(bar_done + 14 * 8, 0);
      STAGE_ACC_LN(accv, pV0, pV1, csa + 1024, 4);
      PROF(5 + l * 16);

      if (!(l & 1)) {
        if (warp == 7) bar_arrive<BAR_HSEND2, 64>();
        mbar_wait(bar_done + 15 * 8, 0);
        STAGE_ACC_LN(acck, pK0, pK1, csa + 512, 8);
        if (warp == 7) bar_arrive<BAR_HSEND, 64>();
        if (warp == 3) bar_arrive<BAR_MID, 64>();
        STAGE_ACC_LN(accq, pQ0, pQ1, csa, 8);
        bar_wg(wg);
        if (warp == 4) bar_sync<BAR_MID, 64>();
        PROF(6 + l * 16);
        const uint32_t halo = sbase + 10 * SLOT;
        if (warp == 0) {
          if (mm > 0) {
            const uint32_t tag = ep1 * 4 + l;
            const uint4* src = g_halo + (size_t)((mm - 1) * 8 + jj) * 1024 + lane;
            int it = 0;
            bool ok;
            do {
              uint4 v[32];
#pragma unroll
              for (int i = 0; i < 32; i++)
                asm volatile("{\n.reg .b64 a, b;\nld.relaxed.gpu.global.v2.b64 {a, b}, [%4];\nmov.b64 {%0, %1}, a;\nmov.b64 {%2, %3}, b;\n}\n"
                             : "=r"(v[i].x), "=r"(v[i].y), "=r"(v[i].z), "=r"(v[i].w) : "l"(src + i * 32) : "memory");
              uint32_t bad = 0;
#pragma unroll
              for (int i = 0; i < 32; i++) {
                bad |= (v[i].y ^ tag) | (v[i].w ^ tag);
                asm volatile("st.shared.v2.u32 [%0], {%1, %2};" :: "r"(halo + i * 256 + lane * 8), "r"(v[i].x), "r"(v[i].z) : "memory");
              }
              ok = __all_sync(0xffffffffu, bad == 0);
            } while (!ok && ++it < (1 << 16));
          } else {
#pragma unroll 1
            for (int i = 0; i < 16; i++) sts128(halo + i * 512 + lane * 16, 0, 0, 0, 0);
            __syncwarp();
          }
          bar_arrive<BAR_HRECV, 64>();
        }
        PROF(7 + l * 16);
        const float sc = 0.17677669529663687f * LOG2E;
        const int e = g & 1;
        uint32_t vmaskA = 0, vmask0 = 0;
#pragma unroll
        for (int jb = 0; jb < 4; jb++) {
          const int c = jb * 8 + 2 * t + e;
          const int d0 = g + 16 - c, d1 = g + 24 - c;
          if (d0 >= 0 && d0 <= 14) { vmaskA |= 1u << jb; if (c >= 16) vmask0 |= 1u << jb; }
          if (d1 >= 0 && d1 <= 14) { vmaskA |= 16u << jb; if (c >= 16) vmask0 |= 16u << jb; }
        }
#pragma unroll 1
        for (int it = (warp == 0 ? 2 : 0); it < (warp < 2 ? 3 : 2); it++) {
          const int hp = (it < 2) ? it : warp;
          const int rb0 = (it < 2) ? r0 : 0;
          if (it == 2 && warp == 1) bar_sync<BAR_HRECV, 64>();
          const uint32_t vmask = (rb0 == 0 && mm == 0) ? vmask0 : vmaskA;
          const uint32_t qb = (hp ? pQ1 : pQ0) + (rb0 + (lane & 15)) * 128;
          const uint32_t kb1 = (hp ? pK1 : pK0) + rb0 * 128, vb1 = (hp ? pV1 : pV0) + rb0 * 128;
          const uint32_t kb0 = rb0 ? kb1 - 2048 : halo + hp * 2048, vb0 = rb0 ? vb1 - 2048 : halo + 4096 + hp * 2048;
          uint32_t qa[2][2][4];
#pragma unroll
          for (int hh = 0; hh < 2; hh++)
#pragma unroll
            for (int ks = 0; ks < 2; ks++) ldsm_x4(qb + ((hh * 64 + ks * 32 + lhi) ^ lsw), qa[hh][ks][0], qa[hh][ks][1], qa[hh][ks][2], qa[hh][ks][3]);
          float s[2][4][4];
#pragma unroll
          for (int jb = 0; jb < 4; jb++) {
            const uint32_t ka = ((jb < 2) ? kb0 : kb1) + ((jb & 1) * 8 + (lane & 7)) * 128;
#pragma unroll
            for (int hh = 0; hh < 2; hh++) {
              uint32_t b0, b1, b2, b3;
              ldsm_x4(ka + ((hh * 64 + ((lane >> 3) << 4)) ^ lsw), b0, b1, b2, b3);
              s[hh][jb][0] = s[hh][jb][1] = s[hh][jb][2] = s[hh][jb][3] = 0.f;
              mma_bf16(s[hh][jb], qa[hh][0][0], qa[hh][0][1], qa[hh][0][2], qa[hh][0][3], b0, b1);
              mma_bf16(s[hh][jb], qa[hh][1][0], qa[hh][1][1], qa[hh][1][2], qa[hh][1][3], b2, b3);
            }
          }
          float v[2][2][4], mx[2][2], sum[2][2];
#pragma unroll
          for (int hh = 0; hh < 2; hh++) {
            mx[hh][0] = mx[hh][1] = -INFINITY;
#pragma unroll
            for (int jb = 0; jb < 4; jb++) {
              const float a0 = e ? s[hh][jb][1] : s[hh][jb][0];
              const float a1 = e ? s[hh][jb][3] : s[hh][jb][2];
              v[hh][0][jb] = (vmask >> jb) & 1 ? a0 : -INFINITY;
              v[hh][1][jb] = (vmask >> (4 + jb)) & 1 ? a1 : -INFINITY;
              mx[hh][0] = fmaxf(mx[hh][0], v[hh][0][jb]); mx[hh][1] = fmaxf(mx[hh][1], v[hh][1][jb]);
            }
          }
#pragma unroll
          for (int o = 1; o <= 2; o <<= 1)
#pragma unroll
            for (int hh = 0; hh < 2; hh++)
#pragma unroll
              for (int r = 0; r < 2; r++) mx[hh][r] = fmaxf(mx[hh][r], __shfl_xor_sync(0xffffffffu, mx[hh][r], o));
#pragma unroll
          for (int hh = 0; hh < 2; hh++)
#pragma unroll
            for (int r = 0; r < 2; r++) {
              const float nb = -mx[hh][r] * sc;
              sum[hh][r] = 0.f;
#pragma unroll
              for (int jb = 0; jb < 4; jb++) { v[hh][r][jb] = ex2(fmaf(v[hh][r][jb], sc, nb)); sum[hh][r] += v[hh][r][jb]; }
            }
#pragma unroll
          for (int o = 1; o <= 2; o <<= 1)
#pragma unroll
            for (int hh = 0; hh < 2; hh++)
#pragma unroll
              for (int r = 0; r < 2; r++) sum[hh][r] += __shfl_xor_sync(0xffffffffu, sum[hh][r], o);
          const uint32_t esh = e * 16;
          float o[2][4][4];
#pragma unroll
          for (int hh = 0; hh < 2; hh++) {
            const float i0 = rcp_fast(sum[hh][0]), i1 = rcp_fast(sum[hh][1]);
#pragma unroll
            for (int dj = 0; dj < 4; dj++) { o[hh][dj][0] = o[hh][dj][1] = o[hh][dj][2] = o[hh][dj][3] = 0.f; }
#pragma unroll
            for (int ks = 0; ks < 2; ks++) {
              const uint32_t pa0 = pack_bf16(v[hh][0][2 * ks] * i0, 0.f) << esh, pa1 = pack_bf16(v[hh][1][2 * ks] * i1, 0.f) << esh;
              const uint32_t pa2 = pack_bf16(v[hh][0][2 * ks + 1] * i0, 0.f) << esh, pa3 = pack_bf16(v[hh][1][2 * ks + 1] * i1, 0.f) << esh;
              const uint32_t va = (ks ? vb1 : vb0) + (lane & 15) * 128;
#pragma unroll
              for (int dp = 0; dp < 2; dp++) {
                uint32_t b0, b1, b2, b3;
                ldsm_x4_t(va + ((hh * 64 + dp * 32 + lhi) ^ lsw), b0, b1, b2, b3);
                mma_bf16(o[hh][dp * 2], pa0, pa1, pa2, pa3, b0, b1);
                mma_bf16(o[hh][dp * 2 + 1], pa0, pa1, pa2, pa3, b2, b3);
              }
            }
          }
#pragma unroll
          for (int hh = 0; hh < 2; hh++)
#pragma unroll
            for (int dp = 0; dp < 2; dp++)
              stsm_x4(qb + ((hh * 64 + dp * 32 + lhi) ^ lsw), pack_bf16(o[hh][dp * 2][0], o[hh][dp * 2][1]), pack_bf16(o[hh][dp * 2][2], o[hh][dp * 2][3]),
                      pack_bf16(o[hh][dp * 2 + 1][0], o[hh][dp * 2 + 1][1]), pack_bf16(o[hh][dp * 2 + 1][2], o[hh][dp * 2 + 1][3]));
        }
      } else {
        const float c0 = rs0 * LOG2E, c1 = rs1 * LOG2E;
        float* kvg = g_kv[par][l >> 1] + (size_t)(jj * 4) * KVH;
        float p[2][4][4];
        PHI_LOAD(acck, 0, csa + 512);
#pragma unroll 1
        for (int it = 0; it < 4; it++) {
          const uint32_t dst0 = ((it & 1) ? pQ0 : pK0) + srowoff, dst1 = ((it & 1) ? pQ1 : pK1) + srowoff;
          float mx[2][2], mn[2][2];
#pragma unroll
          for (int hh = 0; hh < 2; hh++) {
            float mx0 = p[hh][0][0], mn0 = p[hh][0][0], mx1 = p[hh][0][2], mn1 = p[hh][0][2];
#pragma unroll
            for (int j = 0; j < 4; j++) {
              mx0 = fmaxf(mx0, fmaxf(p[hh][j][0], p[hh][j][1])); mn0 = fminf(mn0, fminf(p[hh][j][0], p[hh][j][1]));
              mx1 = fmaxf(mx1, fmaxf(p[hh][j][2], p[hh][j][3])); mn1 = fminf(mn1, fminf(p[hh][j][2], p[hh][j][3]));
            }
            mx[hh][0] = mx0; mx[hh][1] = mx1; mn[hh][0] = mn0; mn[hh][1] = mn1;
          }
#pragma unroll
          for (int o = 1; o <= 2; o <<= 1)
#pragma unroll
            for (int hh = 0; hh < 2; hh++)
#pragma unroll
              for (int r = 0; r < 2; r++) {
                mx[hh][r] = fmaxf(mx[hh][r], __shfl_xor_sync(0xffffffffu, mx[hh][r], o));
                mn[hh][r] = fminf(mn[hh][r], __shfl_xor_sync(0xffffffffu, mn[hh][r], o));
              }
          float en[2][4][4];
          float sp[2][2], sn[2][2];
#pragma unroll
          for (int hh = 0; hh < 2; hh++) {
            const float x0 = -mx[hh][0] * c0, x1 = -mx[hh][1] * c1, n0 = mn[hh][0] * c0, n1 = mn[hh][1] * c1;
            float sp0 = 0.f, sn0 = 0.f, sp1 = 0.f, sn1 = 0.f;
#pragma unroll
            for (int j = 0; j < 4; j++) {
              en[hh][j][0] = ex2(fmaf(p[hh][j][0], -c0, n0)); en[hh][j][1] = ex2(fmaf(p[hh][j][1], -c0, n0));
              en[hh][j][2] = ex2(fmaf(p[hh][j][2], -c1, n1)); en[hh][j][3] = ex2(fmaf(p[hh][j][3], -c1, n1));
              p[hh][j][0] = ex2(fmaf(p[hh][j][0], c0, x0)); p[hh][j][1] = ex2(fmaf(p[hh][j][1], c0, x0));
              p[hh][j][2] = ex2(fmaf(p[hh][j][2], c1, x1)); p[hh][j][3] = ex2(fmaf(p[hh][j][3], c1, x1));
              sp0 += p[hh][j][0] + p[hh][j][1]; sp1 += p[hh][j][2] + p[hh][j][3];
              sn0 += en[hh][j][0] + en[hh][j][1]; sn1 += en[hh][j][2] + en[hh][j][3];
            }
            sp[hh][0] = sp0; sp[hh][1] = sp1; sn[hh][0] = sn0; sn[hh][1] = sn1;
          }
#pragma unroll
          for (int o = 1; o <= 2; o <<= 1)
#pragma unroll
            for (int hh = 0; hh < 2; hh++)
#pragma unroll
              for (int r = 0; r < 2; r++) {
                sp[hh][r] += __shfl_xor_sync(0xffffffffu, sp[hh][r], o);
                sn[hh][r] += __shfl_xor_sync(0xffffffffu, sn[hh][r], o);
              }
          if (it == 0) mbar_wait(bar_done + 15 * 8, 0);
          if (it == 2) bar_sync<BAR_CONS, 256>();
#pragma unroll
          for (int hh = 0; hh < 2; hh++) {
            const float sp0 = rcp_fast(sp[hh][0]), sp1 = rcp_fast(sp[hh][1]), sn0 = rcp_fast(sn[hh][0]), sn1 = rcp_fast(sn[hh][1]);
            const uint32_t dst = hh ? dst1 : dst0;
#pragma unroll
            for (int ks = 0; ks < 2; ks++) {
              stsm_x4(dst + ((ks * 32 + lhi) ^ lsw),
                      pack_bf16(p[hh][2 * ks][0] * sp0, p[hh][2 * ks][1] * sp0), pack_bf16(p[hh][2 * ks][2] * sp1, p[hh][2 * ks][3] * sp1),
                      pack_bf16(p[hh][2 * ks + 1][0] * sp0, p[hh][2 * ks + 1][1] * sp0), pack_bf16(p[hh][2 * ks + 1][2] * sp1, p[hh][2 * ks + 1][3] * sp1));
              stsm_x4(dst + ((64 + ks * 32 + lhi) ^ lsw),
                      pack_bf16(en[hh][2 * ks][0] * sn0, en[hh][2 * ks][1] * sn0), pack_bf16(en[hh][2 * ks][2] * sn1, en[hh][2 * ks][3] * sn1),
                      pack_bf16(en[hh][2 * ks + 1][0] * sn0, en[hh][2 * ks + 1][1] * sn0), pack_bf16(en[hh][2 * ks + 1][2] * sn1, en[hh][2 * ks + 1][3] * sn1));
            }
          }
          if (it == 1) {
            fence_proxy_async_smem();
            bar_sync<BAR_CONS, 256>();
            PROF(6 + l * 16);
            float kv0[16], kv1[16], z0[4], z1[4];
            ACC_DEF(kv0, 16); ACC_DEF(kv1, 16); ACC_DEF(z0, 4); ACC_DEF(z1, 4);
            const uint64_t dp0 = make_desc(wg ? pQ0 : pK0, 16, 1024), dp1 = make_desc(wg ? pQ1 : pK1, 16, 1024);
            const uint64_t dv = make_desc(wg ? pV1 : pV0, 16, 1024);
            const uint64_t d1 = (uint64_t)(((sbase + OFF_ONES) & 0x3FFFF) >> 4);
            wgmma_fence();
#pragma unroll
            for (int ks = 0; ks < 8; ks++) {
              if (ks == 0) {
                wgmma_n32_tt<0>(kv0, dp0, dv); wgmma_n32_tt<0>(kv1, dp1, dv + 4); wgmma_n8_tt<0>(z0, dp0, d1); wgmma_n8_tt<0>(z1, dp1, d1);
              } else {
                wgmma_n32_tt<1>(kv0, dp0 + ks * 128, dv + ks * 128);
                wgmma_n32_tt<1>(kv1, dp1 + ks * 128, dv + 4 + ks * 128);
                wgmma_n8_tt<1>(z0, dp0 + ks * 128, d1);
                wgmma_n8_tt<1>(z1, dp1 + ks * 128, d1);
              }
            }
            wgmma_commit();
            wgmma_wait<0>();
            ACC_FENCE(kv0, 16); ACC_FENCE(kv1, 16); ACC_FENCE(z0, 4); ACC_FENCE(z1, 4);
            float* rp = kvg + wg * 2 * KVH + ((t >> 1) * 64 + (warp & 3) * 16 + g) * 4 + (t & 1) * 2;
#pragma unroll
            for (int i = 0; i < 4; i++) {
              red_v2(rp + i * 512, kv0[i * 4], kv0[i * 4 + 1]); red_v2(rp + i * 512 + 32, kv0[i * 4 + 2], kv0[i * 4 + 3]);
              red_v2(rp + KVH + i * 512, kv1[i * 4], kv1[i * 4 + 1]); red_v2(rp + KVH + i * 512 + 32, kv1[i * 4 + 2], kv1[i * 4 + 3]);
            }
            if (t == 0) {
              red_f32(rp + 2048, z0[0]); red_f32(rp + 2048 + 32, z0[2]);
              red_f32(rp + KVH + 2048, z1[0]); red_f32(rp + KVH + 2048 + 32, z1[2]);
            }
            bar_arrive<BAR_KV, 288>();
            PROF(7 + l * 16);
          }
          if (it == 0) { PHI_LOAD(acck, 32, csa + 768); }
          else if (it == 1) { PHI_LOAD(accq, 0, csa); }
          else if (it == 2) { PHI_LOAD(accq, 32, csa + 256); }
        }
        PROF(8 + l * 16);
        {
          if (lane == 0) wait_flag(&g_flags.kvready[l >> 1][jj], ep1 * 16);
          __syncwarp();
          PROF(9 + l * 16);
          const int f = tid & 63, h = tid >> 6;
          const float4* src = reinterpret_cast<const float4*>(kvg + h * KVH) + f;
          float4 v[8];
#pragma unroll
          for (int i = 0; i < 8; i++) v[i] = __ldcg(src + i * 64);
          const float z = __ldcg(reinterpret_cast<const float*>(src + 512));
          const uint32_t dst = pV0 + h * 8192 + f * 128;
#pragma unroll
          for (int c = 0; c < 4; c++)
            sts128(dst + ((c << 4) ^ lsw), pack_bf16(v[2 * c].x, v[2 * c].y), pack_bf16(v[2 * c].z, v[2 * c].w),
                   pack_bf16(v[2 * c + 1].x, v[2 * c + 1].y), pack_bf16(v[2 * c + 1].z, v[2 * c + 1].w));
          sts128(dst + (64u ^ lsw), pack_bf16(z, 0.f), 0, 0, 0);
        }
        fence_proxy_async_smem();
        bar_sync<BAR_CONS, 256>();
        PROF(10 + l * 16);
        float o[4][20];
        ACC_DEF(o[0], 20); ACC_DEF(o[1], 20); ACC_DEF(o[2], 20); ACC_DEF(o[3], 20);
        wgmma_fence();
#pragma unroll
        for (int h = 0; h < 4; h++) {
          const uint64_t da = make_desc((h == 0 ? pK0 : h == 1 ? pK1 : h == 2 ? pQ0 : pQ1) + wg * 8192, 16, 1024);
          const uint64_t db = make_desc(pV0 + h * 8192, 16, 1024);
#pragma unroll
          for (int ks = 0; ks < 4; ks++) { if (ks == 0) wgmma_n40<0>(o[h], da, db); else wgmma_n40<1>(o[h], da + ks * 2, db + ks * 128); }
        }
        wgmma_commit();
        wgmma_wait<0>();
        ACC_FENCE(o[0], 20); ACC_FENCE(o[1], 20); ACC_FENCE(o[2], 20); ACC_FENCE(o[3], 20);
        bar_wg(wg);
#pragma unroll
        for (int h = 0; h < 4; h++) {
          const float i0 = rcp_fast(__shfl_sync(0xffffffffu, o[h][16], lane & ~3) + 1e-6f);
          const float i1 = rcp_fast(__shfl_sync(0xffffffffu, o[h][18], lane & ~3) + 1e-6f);
          const uint32_t ob = ((h >> 1) ? pQ1 : pQ0) + srowoff;
#pragma unroll
          for (int dp = 0; dp < 2; dp++)
            stsm_x4(ob + (((h & 1) * 64 + dp * 32 + lhi) ^ lsw),
                    pack_bf16(o[h][dp * 8 + 0] * i0, o[h][dp * 8 + 1] * i0), pack_bf16(o[h][dp * 8 + 2] * i1, o[h][dp * 8 + 3] * i1),
                    pack_bf16(o[h][dp * 8 + 4] * i0, o[h][dp * 8 + 5] * i0), pack_bf16(o[h][dp * 8 + 6] * i1, o[h][dp * 8 + 7] * i1));
        }
      }
      fence_proxy_async_smem();
      bar_arrive<BAR_O, 288>();
      if (lane < 2) mbar_arrive_remote(bar_epi, lane);
      PROF(11 + l * 16);

      {
        float acc[64];
        const uint32_t pX0 = sbase + OFF_X, pX1 = pX0 + SLOT;
#pragma unroll
        for (int j = 0; j < 16; j += 2) {
          uint32_t x0, x1, x2, x3;
          ldsm_x4(((j < 8) ? pX0 : pX1) + srowoff + ((((uint32_t)(j & 7) << 4) + lhi) ^ lsw), x0, x1, x2, x3);
          acc[j * 4 + 0] = bf_lo(x0); acc[j * 4 + 1] = bf_hi(x0); acc[j * 4 + 2] = bf_lo(x1); acc[j * 4 + 3] = bf_hi(x1);
          acc[j * 4 + 4] = bf_lo(x2); acc[j * 4 + 5] = bf_hi(x2); acc[j * 4 + 6] = bf_lo(x3); acc[j * 4 + 7] = bf_hi(x3);
        }
        ACC_FENCE(acc, 64);
        bar_wg(wg);
#pragma unroll 1
        for (int s = 0; s < 16; s++) {
          const uint64_t da = make_desc(sbase + (uint32_t)((WO_ASLOT >> (4 * s)) & 15) * SLOT + wg * 8192, 16, 1024);
          const uint64_t db = make_desc(sbase + (uint32_t)((WO_BSLOT >> (4 * s)) & 15) * SLOT, 8192, 1024);
          mbar_wait(bar_full + s * 8, 1);
          if (s == 0) PROF(12 + l * 16);
          if (s == 2) PROF(13 + l * 16);
          wgmma_fence();
#pragma unroll
          for (int k4 = 0; k4 < 4; k4++) wgmma_n128<1>(acc, da + k4 * 2, db + k4 * 128);
          wgmma_commit();
          if (s > 0) { wgmma_wait<1>(); if (lane < 2) mbar_arrive_remote(bar_done + (s - 1) * 8, lane); }
        }
        wgmma_wait<0>();
        ACC_FENCE(acc, 64);
        if (lane < 2) mbar_arrive_remote(bar_done + 15 * 8, lane);
        PROF(14 + l * 16);
#pragma unroll
        for (int j = 0; j < 16; j += 2)
          stsm_x4(((j < 8) ? pX0 : pX1) + srowoff + ((((uint32_t)(j & 7) << 4) + lhi) ^ lsw),
                  pack_bf16(acc[j * 4 + 0], acc[j * 4 + 1]), pack_bf16(acc[j * 4 + 2], acc[j * 4 + 3]),
                  pack_bf16(acc[j * 4 + 4], acc[j * 4 + 5]), pack_bf16(acc[j * 4 + 6], acc[j * 4 + 7]));
        fence_proxy_async_smem();
        bar_arrive<BAR_X, 352>();
        bar_wg(wg);
        PROF(15 + l * 16);
      }
    }
    if (tid == 0) {
      unsigned old = atomicAdd(&g_flags.done, 1);
      if (old == ep1 * NMAIN - 1) {
        asm volatile("st.relaxed.gpu.global.u32 [%0], %1;" :: "l"(&g_flags.epoch), "r"(ep1) : "memory");
      }
    }
    __syncwarp();
    cluster_sync();
  }
}

typedef CUresult (*PFN_encode)(CUtensorMap*, CUtensorMapDataType, cuuint32_t, void*, const cuuint64_t*, const cuuint64_t*,
                               const cuuint32_t*, const cuuint32_t*, CUtensorMapInterleave, CUtensorMapSwizzle,
                               CUtensorMapL2promotion, CUtensorMapFloatOOBfill);

CUtensorMap make_map(PFN_encode enc, const void* ptr, uint64_t inner, uint64_t outer, uint32_t box_inner, uint32_t box_outer) {
  CUtensorMap m;
  cuuint64_t dims[2] = {inner, outer};
  cuuint64_t strides[1] = {inner * 2};
  cuuint32_t box[2] = {box_inner, box_outer};
  cuuint32_t es[2] = {1, 1};
  enc(&m, CU_TENSOR_MAP_DATA_TYPE_BFLOAT16, 2, const_cast<void*>(ptr), dims, strides, box, es, CU_TENSOR_MAP_INTERLEAVE_NONE,
      CU_TENSOR_MAP_SWIZZLE_128B, CU_TENSOR_MAP_L2_PROMOTION_L2_256B, CU_TENSOR_MAP_FLOAT_OOB_FILL_NONE);
  return m;
}

}

extern "C" void kernel_launch(void* const* d_in, const int* in_sizes, int n_in, void* d_out, int out_size) {
  (void)in_sizes; (void)n_in; (void)out_size;
  static PFN_encode enc = nullptr;
  if (!enc) {
    void* fn = nullptr;
    cudaDriverEntryPointQueryResult qr;
    cudaGetDriverEntryPoint("cuTensorMapEncodeTiled", &fn, cudaEnableDefault, &qr);
    enc = (PFN_encode)fn;
    cudaFuncSetAttribute(mega_kernel, cudaFuncAttributeMaxDynamicSharedMemorySize, SMEM_BYTES);
  }
  Params prm;
  prm.wA_qkv = (const __nv_bfloat16*)d_in[1];
  prm.wA_o = (const __nv_bfloat16*)d_in[2];
  prm.wB_qkv = (const __nv_bfloat16*)d_in[4];
  prm.wB_phi = (const __nv_bfloat16*)d_in[5];
  prm.wB_o = (const __nv_bfloat16*)d_in[6];
  void *obuf = nullptr, *wf = nullptr;
  cudaGetSymbolAddress(&obuf, g_obuf);
  cudaGetSymbolAddress(&wf, g_wfold);
  CUtensorMap tm_x0 = make_map(enc, d_in[0], D_MODEL, S_LEN, 64, 128);
  CUtensorMap tm_xo = make_map(enc, d_out, D_MODEL, S_LEN, 64, 128);
  CUtensorMap tm_o = make_map(enc, obuf, D_MODEL, S_LEN, 64, 128);
  CUtensorMap tm_wf = make_map(enc, wf, 2048, D_MODEL, 64, 64);
  CUtensorMap tm_wqA = make_map(enc, d_in[1], 3 * D_MODEL, D_MODEL, 64, 64);
  CUtensorMap tm_wqB = make_map(enc, prm.wB_qkv, 3 * D_MODEL, D_MODEL, 64, 64);
  CUtensorMap tm_woA = make_map(enc, prm.wA_o, D_MODEL, D_MODEL, 64, 64);
  CUtensorMap tm_woB = make_map(enc, prm.wB_o, D_MODEL, D_MODEL, 64, 64);
  mega_kernel<<<NMAIN + NAUX, 384, SMEM_BYTES>>>(tm_x0, tm_xo, tm_o, tm_wf, tm_wqA, tm_wqB, tm_woA, tm_woB, prm);
}
```

```cpp
#include <cuda_runtime.h>
#include <cuda.h>
#include <cuda_bf16.h>
#include <stdint.h>

#define NLAYERS 4

namespace {

constexpr int S_LEN = 2048, D_MODEL = 1024;
constexpr int NAUX = 4, NMAIN = 128;
constexpr int SLOT = 16384;
constexpr int OFF_X = 12 * SLOT;
constexpr int OFF_BAR = 14 * SLOT;
constexpr int OFF_ONES = OFF_BAR + 384;
constexpr int OFF_ST = OFF_BAR + 512;
constexpr int OFF_CS = OFF_ST + 1024;
constexpr int SMEM_BYTES = OFF_CS + 1536;
constexpr unsigned long long WO_ASLOT = 0x8754218754218754ull;
constexpr unsigned long long WO_BSLOT = 0xA9B630A9B630A9B6ull;
__device__ __forceinline__ int kslice(int j, int i) { return i < 2 ? 2 * j + i : (i < 9 ? 2 * ((j + i - 1) & 7) : 2 * ((j + i) & 7) + 1); }
constexpr int KVH = 8 * 64 * 4;
constexpr int KVTOT = 32 * KVH + 32 * 64;

struct Flags {
  unsigned xready[4][16][2];
  unsigned oready[4][16][2];
  unsigned kvready[2][8];
  unsigned csready[2];
  unsigned wfready[8];
  unsigned done;
  unsigned epoch;
  unsigned error;
};

__device__ Flags g_flags;
__device__ __nv_bfloat16 g_obuf[S_LEN * D_MODEL];
__device__ __nv_bfloat16 g_wfold[D_MODEL * 2048];
__device__ uint4 g_halo[16 * 8 * 1024];
__device__ float g_kv[2][2][KVTOT];
__device__ float g_colsum[2][3072];
__device__ uint4 g_stats[S_LEN * 8];

#define PROFT(i) do {} while (0)
#define PROF(i) do {} while (0)

__device__ __forceinline__ uint32_t smem_u32(const void* p) { return (uint32_t)__cvta_generic_to_shared(p); }
__device__ __forceinline__ bool elect_one() {
  uint32_t p;
  asm volatile("{\n.reg .pred p;\nelect.sync _|p, 0xffffffff;\nselp.u32 %0, 1, 0, p;\n}\n" : "=r"(p));
  return p != 0;
}
__device__ __forceinline__ void mbar_init(uint32_t bar, uint32_t cnt) {
  asm volatile("mbarrier.init.shared::cta.b64 [%0], %1;" :: "r"(bar), "r"(cnt));
}
__device__ __forceinline__ void mbar_expect_tx(uint32_t bar, uint32_t bytes) {
  asm volatile("mbarrier.arrive.expect_tx.shared::cta.b64 _, [%0], %1;" :: "r"(bar), "r"(bytes) : "memory");
}
__device__ __forceinline__ void mbar_wait(uint32_t bar, uint32_t parity) {
  uint32_t ok;
  int it = 0;
  do {
    asm volatile("{\n.reg .pred p;\nmbarrier.try_wait.parity.shared::cta.b64 p, [%1], %2;\nselp.u32 %0, 1, 0, p;\n}\n"
                 : "=r"(ok) : "r"(bar), "r"(parity) : "memory");
  } while (!ok && ++it < (1 << 20));
}
__device__ __forceinline__ void mbar_arrive_local(uint32_t bar) {
  asm volatile("mbarrier.arrive.shared::cta.b64 _, [%0];" :: "r"(bar) : "memory");
}
__device__ __forceinline__ void mbar_arrive_remote(uint32_t bar, uint32_t cta_rank) {
  asm volatile("{\n.reg .b32 ra;\nmapa.shared::cluster.u32 ra, %0, %1;\nmbarrier.arrive.shared::cluster.b64 _, [ra];\n}\n"
               :: "r"(bar), "r"(cta_rank) : "memory");
}
__device__ __forceinline__ void tma_load_2d(uint32_t dst, const CUtensorMap* tm, uint32_t bar, int c0, int c1) {
  asm volatile("cp.async.bulk.tensor.2d.shared::cluster.global.mbarrier::complete_tx::bytes [%0], [%1, {%3, %4}], [%2];"
               :: "r"(dst), "l"(tm), "r"(bar), "r"(c0), "r"(c1) : "memory");
}
__device__ __forceinline__ void tma_load_2d_mc(uint32_t dst, const CUtensorMap* tm, uint32_t bar, int c0, int c1) {
  asm volatile("cp.async.bulk.tensor.2d.shared::cluster.global.mbarrier::complete_tx::bytes.multicast::cluster [%0], [%1, {%3, %4}], [%2], %5;"
               :: "r"(dst), "l"(tm), "r"(bar), "r"(c0), "r"(c1), "h"((uint16_t)3) : "memory");
}
__device__ __forceinline__ void tma_store_2d(const CUtensorMap* tm, uint32_t src, int c0, int c1) {
  asm volatile("cp.async.bulk.tensor.2d.global.shared::cta.bulk_group [%0, {%2, %3}], [%1];"
               :: "l"(tm), "r"(src), "r"(c0), "r"(c1) : "memory");
}
__device__ __forceinline__ void bulk_commit_wait() {
  asm volatile("cp.async.bulk.commit_group;\ncp.async.bulk.wait_group 0;" ::: "memory");
}
__device__ __forceinline__ void prefetch_l2(const void* p, uint32_t bytes) {
  asm volatile("cp.async.bulk.prefetch.L2.global [%0], %1;" :: "l"(p), "r"(bytes) : "memory");
}
__device__ __forceinline__ void prefetch_tmap(const CUtensorMap* tm) {
  asm volatile("prefetch.tensormap [%0];" :: "l"(tm) : "memory");
}
__device__ __forceinline__ void fence_proxy_async_global() { asm volatile("fence.proxy.async.global;" ::: "memory"); }
__device__ __forceinline__ void fence_proxy_async_smem() { asm volatile("fence.proxy.async.shared::cta;" ::: "memory"); }
__device__ __forceinline__ void wait_flag(const unsigned* p, unsigned target) {
  unsigned v;
  int it = 0;
  do {
    asm volatile("ld.acquire.gpu.global.u32 %0, [%1];" : "=r"(v) : "l"(p) : "memory");
  } while ((int)(v - target) < 0 && ++it < (1 << 20));
}
__device__ __forceinline__ void signal_release(unsigned* p) {
  asm volatile("red.release.gpu.global.add.u32 [%0], 1;" :: "l"(p) : "memory");
}
__device__ __forceinline__ void signal_relaxed(unsigned* p) {
  asm volatile("red.relaxed.gpu.global.add.u32 [%0], 1;" :: "l"(p) : "memory");
}
#define SIGNAL_TILE signal_release
template <int ID, int N> __device__ __forceinline__ void bar_arrive() { asm volatile("bar.arrive %0, %1;" :: "n"(ID), "n"(N) : "memory"); }
template <int ID, int N> __device__ __forceinline__ void bar_sync() { asm volatile("bar.sync %0, %1;" :: "n"(ID), "n"(N) : "memory"); }
__device__ __forceinline__ void bar_wg(int wg) { asm volatile("bar.sync %0, 128;" :: "r"(2 + wg) : "memory"); }
__device__ __forceinline__ void cluster_sync() {
  asm volatile("barrier.cluster.arrive.release.aligned;\nbarrier.cluster.wait.acquire.aligned;" ::: "memory");
}
__device__ __forceinline__ void cluster_wait() { asm volatile("barrier.cluster.wait.acquire.aligned;" ::: "memory"); }
enum { BAR_CONS = 1, BAR_KV = 4  , BAR_HRECV = 6, BAR_O = 7, BAR_O1 = 8, BAR_X = 9, BAR_X1 = 10, BAR_MID = 11, BAR_WF = 12 };

__device__ __forceinline__ void wgmma_fence() { asm volatile("wgmma.fence.sync.aligned;" ::: "memory"); }
__device__ __forceinline__ void wgmma_commit() { asm volatile("wgmma.commit_group.sync.aligned;" ::: "memory"); }
template <int N> __device__ __forceinline__ void wgmma_wait() { asm volatile("wgmma.wait_group.sync.aligned %0;" :: "n"(N) : "memory"); }

#define ACC64_OUT(d) \
  "+f"(d[0]), "+f"(d[1]), "+f"(d[2]), "+f"(d[3]), "+f"(d[4]), "+f"(d[5]), "+f"(d[6]), "+f"(d[7]), \
  "+f"(d[8]), "+f"(d[9]), "+f"(d[10]), "+f"(d[11]), "+f"(d[12]), "+f"(d[13]), "+f"(d[14]), "+f"(d[15]), \
  "+f"(d[16]), "+f"(d[17]), "+f"(d[18]), "+f"(d[19]), "+f"(d[20]), "+f"(d[21]), "+f"(d[22]), "+f"(d[23]), \
  "+f"(d[24]), "+f"(d[25]), "+f"(d[26]), "+f"(d[27]), "+f"(d[28]), "+f"(d[29]), "+f"(d[30]), "+f"(d[31]), \
  "+f"(d[32]), "+f"(d[33]), "+f"(d[34]), "+f"(d[35]), "+f"(d[36]), "+f"(d[37]), "+f"(d[38]), "+f"(d[39]), \
  "+f"(d[40]), "+f"(d[41]), "+f"(d[42]), "+f"(d[43]), "+f"(d[44]), "+f"(d[45]), "+f"(d[46]), "+f"(d[47]), \
  "+f"(d[48]), "+f"(d[49]), "+f"(d[50]), "+f"(d[51]), "+f"(d[52]), "+f"(d[53]), "+f"(d[54]), "+f"(d[55]), \
  "+f"(d[56]), "+f"(d[57]), "+f"(d[58]), "+f"(d[59]), "+f"(d[60]), "+f"(d[61]), "+f"(d[62]), "+f"(d[63])
#define ACC64_REGS \
  "{%0,%1,%2,%3,%4,%5,%6,%7,%8,%9,%10,%11,%12,%13,%14,%15,%16,%17,%18,%19,%20,%21,%22,%23,%24,%25,%26,%27,%28,%29,%30,%31," \
  "%32,%33,%34,%35,%36,%37,%38,%39,%40,%41,%42,%43,%44,%45,%46,%47,%48,%49,%50,%51,%52,%53,%54,%55,%56,%57,%58,%59,%60,%61,%62,%63}"

template <int scale_d> __device__ __forceinline__ void wgmma_n128(float (&d)[64], uint64_t descA, uint64_t descB) {
  asm volatile("{\n.reg .pred p;\nsetp.ne.b32 p, %66, 0;\n"
               "wgmma.mma_async.sync.aligned.m64n128k16.f32.bf16.bf16 " ACC64_REGS ", %64, %65, p, 1, 1, 0, 1;\n}\n"
               : ACC64_OUT(d) : "l"(descA), "l"(descB), "n"(scale_d));
}
template <int scale_d> __device__ __forceinline__ void wgmma_n256(float (&d)[128], uint64_t descA, uint64_t descB) {
  asm volatile("{\n.reg .pred p;\nsetp.ne.b32 p, %130, 0;\n"
               "wgmma.mma_async.sync.aligned.m64n256k16.f32.bf16.bf16 {%0,%1,%2,%3,%4,%5,%6,%7,%8,%9,%10,%11,%12,%13,%14,%15,%16,%17,%18,%19,%20,%21,%22,%23,%24,%25,%26,%27,%28,%29,%30,%31,%32,%33,%34,%35,%36,%37,%38,%39,%40,%41,%42,%43,%44,%45,%46,%47,%48,%49,%50,%51,%52,%53,%54,%55,%56,%57,%58,%59,%60,%61,%62,%63,%64,%65,%66,%67,%68,%69,%70,%71,%72,%73,%74,%75,%76,%77,%78,%79,%80,%81,%82,%83,%84,%85,%86,%87,%88,%89,%90,%91,%92,%93,%94,%95,%96,%97,%98,%99,%100,%101,%102,%103,%104,%105,%106,%107,%108,%109,%110,%111,%112,%113,%114,%115,%116,%117,%118,%119,%120,%121,%122,%123,%124,%125,%126,%127}, %128, %129, p, 1, 1, 0, 1;\n}\n"
               : "+f"(d[0]), "+f"(d[1]), "+f"(d[2]), "+f"(d[3]), "+f"(d[4]), "+f"(d[5]), "+f"(d[6]), "+f"(d[7]), "+f"(d[8]), "+f"(d[9]), "+f"(d[10]), "+f"(d[11]), "+f"(d[12]), "+f"(d[13]), "+f"(d[14]), "+f"(d[15]), "+f"(d[16]), "+f"(d[17]), "+f"(d[18]), "+f"(d[19]), "+f"(d[20]), "+f"(d[21]), "+f"(d[22]), "+f"(d[23]), "+f"(d[24]), "+f"(d[25]), "+f"(d[26]), "+f"(d[27]), "+f"(d[28]), "+f"(d[29]), "+f"(d[30]), "+f"(d[31]), "+f"(d[32]), "+f"(d[33]), "+f"(d[34]), "+f"(d[35]), "+f"(d[36]), "+f"(d[37]), "+f"(d[38]), "+f"(d[39]), "+f"(d[40]), "+f"(d[41]), "+f"(d[42]), "+f"(d[43]), "+f"(d[44]), "+f"(d[45]), "+f"(d[46]), "+f"(d[47]), "+f"(d[48]), "+f"(d[49]), "+f"(d[50]), "+f"(d[51]), "+f"(d[52]), "+f"(d[53]), "+f"(d[54]), "+f"(d[55]), "+f"(d[56]), "+f"(d[57]), "+f"(d[58]), "+f"(d[59]), "+f"(d[60]), "+f"(d[61]), "+f"(d[62]), "+f"(d[63]), "+f"(d[64]), "+f"(d[65]), "+f"(d[66]), "+f"(d[67]), "+f"(d[68]), "+f"(d[69]), "+f"(d[70]), "+f"(d[71]), "+f"(d[72]), "+f"(d[73]), "+f"(d[74]), "+f"(d[75]), "+f"(d[76]), "+f"(d[77]), "+f"(d[78]), "+f"(d[79]), "+f"(d[80]), "+f"(d[81]), "+f"(d[82]), "+f"(d[83]), "+f"(d[84]), "+f"(d[85]), "+f"(d[86]), "+f"(d[87]), "+f"(d[88]), "+f"(d[89]), "+f"(d[90]), "+f"(d[91]), "+f"(d[92]), "+f"(d[93]), "+f"(d[94]), "+f"(d[95]), "+f"(d[96]), "+f"(d[97]), "+f"(d[98]), "+f"(d[99]), "+f"(d[100]), "+f"(d[101]), "+f"(d[102]), "+f"(d[103]), "+f"(d[104]), "+f"(d[105]), "+f"(d[106]), "+f"(d[107]), "+f"(d[108]), "+f"(d[109]), "+f"(d[110]), "+f"(d[111]), "+f"(d[112]), "+f"(d[113]), "+f"(d[114]), "+f"(d[115]), "+f"(d[116]), "+f"(d[117]), "+f"(d[118]), "+f"(d[119]), "+f"(d[120]), "+f"(d[121]), "+f"(d[122]), "+f"(d[123]), "+f"(d[124]), "+f"(d[125]), "+f"(d[126]), "+f"(d[127])
               : "l"(descA), "l"(descB), "n"(scale_d));
}
template <int scale_d> __device__ __forceinline__ void wgmma_n32_tt(float (&d)[16], uint64_t descA, uint64_t descB) {
  asm volatile("{\n.reg .pred p;\nsetp.ne.b32 p, %18, 0;\n"
               "wgmma.mma_async.sync.aligned.m64n32k16.f32.bf16.bf16 {%0,%1,%2,%3,%4,%5,%6,%7,%8,%9,%10,%11,%12,%13,%14,%15}, %16, %17, p, 1, 1, 1, 1;\n}\n"
               : "+f"(d[0]), "+f"(d[1]), "+f"(d[2]), "+f"(d[3]), "+f"(d[4]), "+f"(d[5]), "+f"(d[6]), "+f"(d[7]),
                 "+f"(d[8]), "+f"(d[9]), "+f"(d[10]), "+f"(d[11]), "+f"(d[12]), "+f"(d[13]), "+f"(d[14]), "+f"(d[15])
               : "l"(descA), "l"(descB), "n"(scale_d));
}
template <int scale_d> __device__ __forceinline__ void wgmma_n8_tt(float (&d)[4], uint64_t descA, uint64_t descB) {
  asm volatile("{\n.reg .pred p;\nsetp.ne.b32 p, %6, 0;\n"
               "wgmma.mma_async.sync.aligned.m64n8k16.f32.bf16.bf16 {%0,%1,%2,%3}, %4, %5, p, 1, 1, 1, 1;\n}\n"
               : "+f"(d[0]), "+f"(d[1]), "+f"(d[2]), "+f"(d[3]) : "l"(descA), "l"(descB), "n"(scale_d));
}
template <int scale_d> __device__ __forceinline__ void wgmma_n40(float (&d)[20], uint64_t descA, uint64_t descB) {
  asm volatile("{\n.reg .pred p;\nsetp.ne.b32 p, %22, 0;\n"
               "wgmma.mma_async.sync.aligned.m64n40k16.f32.bf16.bf16 {%0,%1,%2,%3,%4,%5,%6,%7,%8,%9,%10,%11,%12,%13,%14,%15,%16,%17,%18,%19}, %20, %21, p, 1, 1, 0, 1;\n}\n"
               : "+f"(d[0]), "+f"(d[1]), "+f"(d[2]), "+f"(d[3]), "+f"(d[4]), "+f"(d[5]), "+f"(d[6]), "+f"(d[7]),
                 "+f"(d[8]), "+f"(d[9]), "+f"(d[10]), "+f"(d[11]), "+f"(d[12]), "+f"(d[13]), "+f"(d[14]), "+f"(d[15]),
                 "+f"(d[16]), "+f"(d[17]), "+f"(d[18]), "+f"(d[19])
               : "l"(descA), "l"(descB), "n"(scale_d));
}
__device__ __forceinline__ uint64_t make_desc(uint32_t addr, uint32_t lbo_bytes, uint32_t sbo_bytes) {
  return (uint64_t)((addr & 0x3FFFF) >> 4) | ((uint64_t)(lbo_bytes >> 4) << 16) | ((uint64_t)(sbo_bytes >> 4) << 32) | (1ull << 62);
}

__device__ __forceinline__ void ldsm_x4(uint32_t addr, uint32_t& r0, uint32_t& r1, uint32_t& r2, uint32_t& r3) {
  asm volatile("ldmatrix.sync.aligned.m8n8.x4.shared.b16 {%0,%1,%2,%3}, [%4];" : "=r"(r0), "=r"(r1), "=r"(r2), "=r"(r3) : "r"(addr) : "memory");
}
__device__ __forceinline__ void ldsm_x4_t(uint32_t addr, uint32_t& r0, uint32_t& r1, uint32_t& r2, uint32_t& r3) {
  asm volatile("ldmatrix.sync.aligned.m8n8.x4.trans.shared.b16 {%0,%1,%2,%3}, [%4];" : "=r"(r0), "=r"(r1), "=r"(r2), "=r"(r3) : "r"(addr) : "memory");
}
__device__ __forceinline__ void stsm_x4(uint32_t addr, uint32_t r0, uint32_t r1, uint32_t r2, uint32_t r3) {
  asm volatile("stmatrix.sync.aligned.m8n8.x4.shared.b16 [%0], {%1,%2,%3,%4};" :: "r"(addr), "r"(r0), "r"(r1), "r"(r2), "r"(r3) : "memory");
}
__device__ __forceinline__ uint4 lds128(uint32_t addr) {
  uint4 v;
  asm volatile("ld.shared.v4.u32 {%0,%1,%2,%3}, [%4];" : "=r"(v.x), "=r"(v.y), "=r"(v.z), "=r"(v.w) : "r"(addr) : "memory");
  return v;
}
__device__ __forceinline__ void sts128(uint32_t addr, uint32_t a, uint32_t b, uint32_t c, uint32_t d) {
  asm volatile("st.shared.v4.u32 [%0], {%1,%2,%3,%4};" :: "r"(addr), "r"(a), "r"(b), "r"(c), "r"(d) : "memory");
}
__device__ __forceinline__ float2 lds64f(uint32_t addr) {
  float2 v;
  asm volatile("ld.shared.v2.f32 {%0,%1}, [%2];" : "=f"(v.x), "=f"(v.y) : "r"(addr) : "memory");
  return v;
}
__device__ __forceinline__ void sts64f(uint32_t addr, float a, float b) {
  asm volatile("st.shared.v2.f32 [%0], {%1,%2};" :: "r"(addr), "f"(a), "f"(b) : "memory");
}
__device__ __forceinline__ float4 lds128f(uint32_t addr) {
  float4 v;
  asm volatile("ld.shared.v4.f32 {%0,%1,%2,%3}, [%4];" : "=f"(v.x), "=f"(v.y), "=f"(v.z), "=f"(v.w) : "r"(addr) : "memory");
  return v;
}
__device__ __forceinline__ void mma_bf16(float (&c)[4], uint32_t a0, uint32_t a1, uint32_t a2, uint32_t a3, uint32_t b0, uint32_t b1) {
  asm("mma.sync.aligned.m16n8k16.row.col.f32.bf16.bf16.f32 {%0,%1,%2,%3}, {%4,%5,%6,%7}, {%8,%9}, {%0,%1,%2,%3};"
               : "+f"(c[0]), "+f"(c[1]), "+f"(c[2]), "+f"(c[3]) : "r"(a0), "r"(a1), "r"(a2), "r"(a3), "r"(b0), "r"(b1));
}
__device__ __forceinline__ uint32_t movm_t(uint32_t v) {
  uint32_t r;
  asm volatile("movmatrix.sync.aligned.m8n8.trans.b16 %0, %1;" : "=r"(r) : "r"(v));
  return r;
}
__device__ __forceinline__ uint32_t pack_bf16(float lo, float hi) {
  uint32_t r;
  asm("cvt.rn.bf16x2.f32 %0, %1, %2;" : "=r"(r) : "f"(hi), "f"(lo));
  return r;
}
__device__ __forceinline__ float bf_lo(uint32_t v) { return __uint_as_float(v << 16); }
__device__ __forceinline__ float bf_hi(uint32_t v) { return __uint_as_float(v & 0xFFFF0000u); }
__device__ __forceinline__ float ex2(float x) { float r; asm("ex2.approx.ftz.f32 %0, %1;" : "=f"(r) : "f"(x)); return r; }
__device__ __forceinline__ float rcp_fast(float x) { float r; asm("rcp.approx.ftz.f32 %0, %1;" : "=f"(r) : "f"(x)); return r; }
__device__ __forceinline__ void red_v4(float* p, float a, float b, float c, float d) {
  asm volatile("red.global.add.v4.f32 [%0], {%1, %2, %3, %4};" :: "l"(p), "f"(a), "f"(b), "f"(c), "f"(d) : "memory");
}
__device__ __forceinline__ void red_v2(float* p, float a, float b) {
  asm volatile("red.global.add.v2.f32 [%0], {%1, %2};" :: "l"(p), "f"(a), "f"(b) : "memory");
}
__device__ __forceinline__ void red_f32(float* p, float a) {
  asm volatile("red.global.add.f32 [%0], %1;" :: "l"(p), "f"(a) : "memory");
}

__device__ __forceinline__ void st_ll(uint4* p, uint32_t d0, uint32_t d1, uint32_t tag) {
  asm volatile("{\n.reg .b64 a, b;\nmov.b64 a, {%1, %3};\nmov.b64 b, {%2, %3};\nst.relaxed.gpu.global.v2.b64 [%0], {a, b};\n}\n"
               :: "l"(p), "r"(d0), "r"(d1), "r"(tag) : "memory");
}
__device__ __forceinline__ uint4 ld_ll(const uint4* p) {
  uint4 v;
  asm volatile("{\n.reg .b64 a, b;\nld.relaxed.gpu.global.v2.b64 {a, b}, [%4];\nmov.b64 {%0, %1}, a;\nmov.b64 {%2, %3}, b;\n}\n"
               : "=r"(v.x), "=r"(v.y), "=r"(v.z), "=r"(v.w) : "l"(p) : "memory");
  return v;
}
__device__ __forceinline__ void bulk_reduce_f32(float* dst, uint32_t src, uint32_t bytes) {
  asm volatile("cp.reduce.async.bulk.global.shared::cta.bulk_group.add.f32 [%0], [%1], %2;" :: "l"(dst), "r"(src), "r"(bytes) : "memory");
}

constexpr float LOG2E = 1.4426950408889634f;

struct Params {
  const __nv_bfloat16* wA_qkv;
  const __nv_bfloat16* wA_o;
  const __nv_bfloat16* wB_qkv;
  const __nv_bfloat16* wB_phi;
  const __nv_bfloat16* wB_o;
  __nv_bfloat16* out;
};

#define ACC_DEF(d, n) _Pragma("unroll") for (int i_ = 0; i_ < (n); i_++) asm volatile("" : "=f"(d[i_]))
#define ACC_FENCE(d, n) _Pragma("unroll") for (int i_ = 0; i_ < (n); i_++) asm volatile("" : "+f"(d[i_]) :: "memory")

#define STAGE_ACC_LN(acc, off, p0, csa, NB, SENDP) \
  _Pragma("unroll") for (int b_ = 0; b_ < 8; b_ += (NB)) { \
    float4 c_[NB]; \
    uint32_t w_[NB][4]; \
    _Pragma("unroll") for (int j_ = 0; j_ < (NB); j_++) c_[j_] = lds128f((csa) + (b_ + j_) * 64); \
    _Pragma("unroll") for (int j_ = 0; j_ < (NB); j_++) { \
      const int o_ = (off) + (b_ + j_) * 8; \
      w_[j_][0] = pack_bf16(rs0 * fmaf(nm0, c_[j_].x, acc[o_ + 0]), rs0 * fmaf(nm0, c_[j_].y, acc[o_ + 1])); \
      w_[j_][1] = pack_bf16(rs1 * fmaf(nm1, c_[j_].x, acc[o_ + 2]), rs1 * fmaf(nm1, c_[j_].y, acc[o_ + 3])); \
      w_[j_][2] = pack_bf16(rs0 * fmaf(nm0, c_[j_].z, acc[o_ + 4]), rs0 * fmaf(nm0, c_[j_].w, acc[o_ + 5])); \
      w_[j_][3] = pack_bf16(rs1 * fmaf(nm1, c_[j_].z, acc[o_ + 6]), rs1 * fmaf(nm1, c_[j_].w, acc[o_ + 7])); \
    } \
    if ((SENDP) >= 0 && hsend) { \
      _Pragma("unroll") for (int j_ = 0; j_ < (NB); j_++) { \
        st_ll(hdst + ((SENDP) * 16 + (b_ + j_) * 2) * 32, w_[j_][0], w_[j_][1], tag); \
        st_ll(hdst + ((SENDP) * 16 + (b_ + j_) * 2 + 1) * 32, w_[j_][2], w_[j_][3], tag); \
      } \
    } \
    _Pragma("unroll") for (int j_ = 0; j_ < (NB); j_++) \
      stsm_x4((p0) + ((b_ + j_) >> 2) * SLOT + srowoff + ((((uint32_t)((b_ + j_) & 3) << 5) + lhi) ^ lsw), w_[j_][0], w_[j_][1], w_[j_][2], w_[j_][3]); \
  }
#define PHI_LOAD(acc, off, csa) \
  _Pragma("unroll") for (int j_ = 0; j_ < 4; j_++) { \
    const float4 c_ = lds128f((csa) + j_ * 64); \
    float (&pa_)[4] = p[j_ >> 1][(j_ & 1) * 2]; float (&pb_)[4] = p[j_ >> 1][(j_ & 1) * 2 + 1]; \
    pa_[0] = fmaf(nm0, c_.x, acc[(off) + j_ * 8 + 0]); pa_[1] = fmaf(nm0, c_.y, acc[(off) + j_ * 8 + 1]); \
    pa_[2] = fmaf(nm1, c_.x, acc[(off) + j_ * 8 + 2]); pa_[3] = fmaf(nm1, c_.y, acc[(off) + j_ * 8 + 3]); \
    pb_[0] = fmaf(nm0, c_.z, acc[(off) + j_ * 8 + 4]); pb_[1] = fmaf(nm0, c_.w, acc[(off) + j_ * 8 + 5]); \
    pb_[2] = fmaf(nm1, c_.z, acc[(off) + j_ * 8 + 6]); pb_[3] = fmaf(nm1, c_.w, acc[(off) + j_ * 8 + 7]); \
  }

__global__ void __cluster_dims__(2, 1, 1) __launch_bounds__(384, 1)
mega_kernel(const __grid_constant__ CUtensorMap tm_x0, const __grid_constant__ CUtensorMap tm_xo,
            const __grid_constant__ CUtensorMap tm_o, const __grid_constant__ CUtensorMap tm_wf,
            const __grid_constant__ CUtensorMap tm_wqA, const __grid_constant__ CUtensorMap tm_wqB,
            const __grid_constant__ CUtensorMap tm_woA, const __grid_constant__ CUtensorMap tm_woB, const Params prm) {
  extern __shared__ __align__(1024) uint8_t smem_raw[];
  const uint32_t sbase = smem_u32(smem_raw);
  const uint32_t bar_full = sbase + OFF_BAR;
  const uint32_t bar_done = bar_full + 128;
  const uint32_t bar_stat = bar_full + 256, bar_epi = bar_full + 264, bar_x0 = bar_full + 272;

  const int warp = threadIdx.x >> 5, lane = threadIdx.x & 31;
  uint32_t rank;
  asm volatile("mov.u32 %0, %%cluster_ctarank;" : "=r"(rank));
  const int cta = (int)blockIdx.x - NAUX;
  const int cl = cta >> 1;
  const int jj = cl & 7, cc = cl >> 3;
  const int mm = cc * 2 + (int)rank;

  unsigned epoch;
  asm volatile("ld.relaxed.gpu.global.u32 %0, [%1];" : "=r"(epoch) : "l"(&g_flags.epoch) : "memory");
  const unsigned ep1 = epoch + 1;
  const int par = ep1 & 1;

  if (cta >= 0) {
    if (threadIdx.x == 0) {
      PROFT(79);
      for (int i = 0; i < 16; i++) { mbar_init(bar_full + i * 8, 1); mbar_init(bar_done + i * 8, 16); }
      mbar_init(bar_stat, 2); mbar_init(bar_epi, 16); mbar_init(bar_x0, 1);
      asm volatile("fence.mbarrier_init.release.cluster;" ::: "memory");
    }
    if (warp == 1) asm volatile("st.shared.u32 [%0], %1;" :: "r"(sbase + OFF_ONES + lane * 4), "r"(0x3F803F80u) : "memory");
    __syncthreads();
    asm volatile("barrier.cluster.arrive.relaxed.aligned;" ::: "memory");
  }

  if (cta < 0) {
    const int w = blockIdx.x * 12 + warp;
    const uint32_t buf = sbase + warp * SLOT, bar = sbase + OFF_BAR + warp * 16;
    const uint32_t lsw = (lane & 7) << 4, lhi = (lane >> 4) << 4, lrow = (lane & 15) * 128;
    const bool el = elect_one();
    if (el) {
      mbar_init(bar, 1); mbar_init(bar + 8, 1);
      asm volatile("fence.mbarrier_init.release.cluster;" ::: "memory");
    }
#pragma unroll 1
    for (int ph = 0; ph < (NLAYERS > 1 ? 2 : 1); ph++) {
      const CUtensorMap* tm = ph ? (w < 32 ? &tm_wf : &tm_wqB) : &tm_wqA;
      if (el) {
        if (ph && w < 32) { wait_flag(&g_flags.wfready[(w & 15) >> 1], ep1 * 16); fence_proxy_async_global(); }
        for (int i = 0; i < 2; i++) { mbar_expect_tx(bar + i * 8, 8192); tma_load_2d(buf + i * 8192, tm, bar + i * 8, w * 64, i * 64); }
      }
      __syncwarp();
      float cs[8][4];
#pragma unroll
      for (int i = 0; i < 8; i++) cs[i][0] = cs[i][1] = cs[i][2] = cs[i][3] = 0.f;
#pragma unroll 1
      for (int n = 0; n < 16; n++) {
        const uint32_t tb = buf + (n & 1) * 8192 + lrow;
        mbar_wait(bar + (n & 1) * 8, (n >> 1) & 1);
#pragma unroll
        for (int i = 0; i < 16; i++) {
          uint32_t b0, b1, b2, b3;
          ldsm_x4_t(tb + (i >> 2) * 2048 + (((i & 3) * 32 + lhi) ^ lsw), b0, b1, b2, b3);
          mma_bf16(cs[2 * (i & 3)], 0x3F803F80u, 0x3F803F80u, 0x3F803F80u, 0x3F803F80u, b0, b1);
          mma_bf16(cs[2 * (i & 3) + 1], 0x3F803F80u, 0x3F803F80u, 0x3F803F80u, 0x3F803F80u, b2, b3);
        }
        __syncwarp();
        if (el && n < 14) { mbar_expect_tx(bar + (n & 1) * 8, 8192); tma_load_2d(buf + (n & 1) * 8192, tm, bar + (n & 1) * 8, w * 64, (n + 2) * 64); }
      }
      if (lane < 4) {
#pragma unroll
        for (int i = 0; i < 8; i++) *reinterpret_cast<float2*>(g_colsum[ph] + w * 64 + i * 8 + lane * 2) = make_float2(cs[i][0], cs[i][1]);
      }
      __syncwarp();
      if (el) {
        signal_release(&g_flags.csready[ph]);
      }
    }
  } else if (warp >= 8) {
    asm volatile("setmaxnreg.dec.sync.aligned.u32 40;");
    if (warp == 8) {
      const bool el = elect_one();
      if (el) prefetch_tmap(&tm_wqA);
      cluster_wait();
      if (el) {
        const int col = jj * 128 + (int)rank * 64;
#pragma unroll 1
        for (int l = 0; l < NLAYERS; l++) {
          const CUtensorMap* tqk = (l & 1) ? &tm_wf : &tm_wqA;
          const CUtensorMap* tv = (l & 1) ? &tm_wqB : &tm_wqA;
          const CUtensorMap* two = (l & 1) ? &tm_woB : &tm_woA;
          if (l == 1) { wait_flag(&g_flags.wfready[jj], ep1 * 16); fence_proxy_async_global(); }
          uint32_t dst = sbase + rank * 8192;
#pragma unroll 1
          for (int i = 0; i < 16; i++) {
            if (i >= 3) mbar_wait(bar_done + (i - 3) * 8, 0);
            else if (l) mbar_wait(bar_done + (11 + 2 * i) * 8, 1);
            const uint32_t fb = bar_full + i * 8;
            mbar_expect_tx(fb, (i < 2) ? 3 * SLOT : 4 * SLOT);
            const int kk = kslice(jj, i);
            tma_load_2d_mc(dst, tqk, fb, col, kk * 64);
            tma_load_2d_mc(dst + SLOT, tqk, fb, col + 1024, kk * 64);
            tma_load_2d_mc(dst + 2 * SLOT, tv, fb, col + 2048, kk * 64);
            dst += 3 * SLOT;
            if (dst >= sbase + 9 * SLOT) dst -= 9 * SLOT;
          }
#pragma unroll 1
          for (int n = 0; n < 16; n++) {
            const int s = (n < 6) ? ((0x342051 >> (4 * n)) & 15) : n;
            if (n >= 6) mbar_wait(bar_done + (n - 6) * 8, 1);
            else if (n == 5) mbar_wait(bar_epi, l & 1);
            else mbar_wait(bar_done + (13 + (n >> 1)) * 8, 0);
            const uint32_t fb = bar_full + s * 8;
            mbar_expect_tx(fb, (s < 2) ? SLOT : 2 * SLOT);
            tma_load_2d_mc(sbase + rank * 8192 + (uint32_t)((WO_BSLOT >> (4 * s)) & 15) * SLOT, two, fb, col, kslice(jj, s) * 64);
          }
        }
      }
      __syncwarp();
    } else if (warp == 9) {
      const bool el = elect_one();
      if (el) {
        mbar_expect_tx(bar_x0, 2 * SLOT);
        tma_load_2d(sbase + OFF_X, &tm_x0, bar_x0, jj * 128, mm * 128);
        tma_load_2d(sbase + OFF_X + SLOT, &tm_x0, bar_x0, jj * 128 + 64, mm * 128);
      }
#pragma unroll 1
      for (int l = 0; l < NLAYERS; l++) {
        if (el) {
          const CUtensorMap* tx = l ? &tm_xo : &tm_x0;
          if (l) {
            mbar_wait(bar_done + 15 * 8, 1);
            wait_flag(&g_flags.xready[l][mm][0], ep1 * 8);
            fence_proxy_async_global();
            PROFT(160 + l * 8);
          }
          uint32_t dst = sbase + 9 * SLOT;
#pragma unroll 1
          for (int i = 2; i < 16; i++) {
            if (i >= 5) mbar_wait(bar_done + (i - 3) * 8, 0);
            if (i == 9 && l) { wait_flag(&g_flags.xready[l][mm][1], ep1 * 8); fence_proxy_async_global(); }
            tma_load_2d(dst, tx, bar_full + i * 8, kslice(jj, i) * 64, mm * 128);
            dst += SLOT;
            if (dst == sbase + 12 * SLOT) dst = sbase + 9 * SLOT;
          }
        }
        if (el) {
          mbar_wait(bar_epi, l & 1);
          wait_flag(&g_flags.oready[l][mm][0], ep1 * 8);
          fence_proxy_async_global();
          PROFT(163 + l * 8);
#pragma unroll 1
          for (int s = 2; s < 16; s++) {
            if (s >= 6) mbar_wait(bar_done + (s - 6) * 8, 1);
            if (s == 7) { wait_flag(&g_flags.oready[l][mm][1], ep1 * 8); fence_proxy_async_global(); }
            tma_load_2d(sbase + (uint32_t)((WO_ASLOT >> (4 * s)) & 15) * SLOT, &tm_o, bar_full + s * 8, kslice(jj, s) * 64, mm * 128);
          }
        }
      }
      __syncwarp();
      cluster_wait();
    } else {
      const int hw = warp - 10, ht = hw * 32 + lane;
      const bool el = elect_one();
      cluster_wait();
      mbar_wait(bar_x0, 0);
      {
        float4* z = reinterpret_cast<float4*>(&g_kv[par ^ 1][0][0]) + cta * (2 * KVTOT / 4 / NMAIN);
#pragma unroll 1
        for (int i = ht; i < 2 * KVTOT / 4 / NMAIN; i += 64) z[i] = make_float4(0.f, 0.f, 0.f, 0.f);
      }
#pragma unroll 1
      for (int l = 0; l < NLAYERS; l++) {
        const uint32_t tag = ep1 * 4 + l;
        if (l) mbar_wait(bar_done, 0);
#pragma unroll 1
        for (int rr = 0; rr < 2; rr++) {
          const uint32_t a = sbase + OFF_X + (hw * 64 + rr * 32 + lane) * 128, sw = (lane & 7) << 4;
          uint32_t w0;
          asm volatile("ld.shared.u32 %0, [%1];" : "=r"(w0) : "r"(a) : "memory");
          const float pv = bf_lo(w0);
          float s0 = 0.f, s1 = 0.f, q0 = 0.f, q1 = 0.f;
#pragma unroll 1
          for (int c = 0; c < 16; c += 4) {
            uint4 v[4];
#pragma unroll
            for (int i = 0; i < 4; i++) v[i] = lds128(a + (c >> 3) * SLOT + ((((c & 7) + i) << 4) ^ sw));
#pragma unroll
            for (int i = 0; i < 4; i++) {
              float d;
              d = bf_lo(v[i].x) - pv; s0 += d; q0 = fmaf(d, d, q0); d = bf_hi(v[i].x) - pv; s1 += d; q1 = fmaf(d, d, q1);
              d = bf_lo(v[i].y) - pv; s0 += d; q0 = fmaf(d, d, q0); d = bf_hi(v[i].y) - pv; s1 += d; q1 = fmaf(d, d, q1);
              d = bf_lo(v[i].z) - pv; s0 += d; q0 = fmaf(d, d, q0); d = bf_hi(v[i].z) - pv; s1 += d; q1 = fmaf(d, d, q1);
              d = bf_lo(v[i].w) - pv; s0 += d; q0 = fmaf(d, d, q0); d = bf_hi(v[i].w) - pv; s1 += d; q1 = fmaf(d, d, q1);
            }
          }
          s0 += s1; q0 += q1;
          const float mu = s0 * (1.f / 128.f);
          st_ll(g_stats + (size_t)(mm * 128 + hw * 64 + rr * 32 + lane) * 8 + jj, __float_as_uint(pv + mu), __float_as_uint(fmaf(-s0, mu, q0)), tag);
        }
        if (l == 0) {
          const char* wrow = reinterpret_cast<const char*>(prm.wB_qkv + (size_t)(mm * 64 + ht) * 3072 + jj * 128);
          prefetch_l2(wrow, 256); prefetch_l2(wrow + 2048, 256);
          if (ht == 63) prefetch_l2(prm.wB_phi + jj * 4096, 8192);
          if (ht < 16) prefetch_l2((const char*)((ht & 8) ? prm.wB_o : prm.wA_o) + (size_t)cta * 16384 + (ht & 7) * 2048, 2048);
        }
#pragma unroll 1
        for (int rr = 0; rr < 2; rr++) {
          const uint4* srow = g_stats + (size_t)(mm * 128 + hw * 64 + rr * 32 + lane) * 8;
          float sm[8], m2 = 0.f;
#pragma unroll
          for (int hf = 0; hf < 2; hf++) {
            uint32_t bad;
            int it = 0;
            float q;
            do {
              bad = 0; q = 0.f;
#pragma unroll
              for (int i = 0; i < 4; i++) {
                const uint4 v = ld_ll(srow + hf * 4 + i);
                sm[hf * 4 + i] = __uint_as_float(v.x); q += __uint_as_float(v.z);
                bad |= (v.y ^ tag) | (v.w ^ tag);
              }
            } while (bad && ++it < (1 << 18));
            m2 += q;
          }
          const float mean = (((sm[0] + sm[1]) + (sm[2] + sm[3])) + ((sm[4] + sm[5]) + (sm[6] + sm[7]))) * 0.125f;
          float dd = 0.f;
#pragma unroll
          for (int i = 0; i < 8; i++) { const float e = sm[i] - mean; dd = fmaf(e, e, dd); }
          const float rs = rsqrtf(fmaxf(fmaf(dd, 128.f, m2), 0.f) * (1.f / 1024.f) + 1e-5f);
          asm volatile("st.shared.v2.f32 [%0], {%1, %2};" :: "r"(sbase + OFF_ST + (hw * 64 + rr * 32 + lane) * 8), "f"(rs), "f"(-mean) : "memory");
        }
        {
          if (l < 2 && el) wait_flag(&g_flags.csready[l], ep1 * 48);
          __syncwarp();
          const float2* src = reinterpret_cast<const float2*>(g_colsum[l & 1] + jj * 128) + ht;
          const uint32_t dst = sbase + OFF_CS + (ht >> 3) * 64 + (ht & 3) * 16 + ((ht >> 2) & 1) * 8;
#pragma unroll
          for (int p = 0; p < 3; p++) {
            const float2 v = __ldcg(src + p * 512);
            asm volatile("st.shared.v2.f32 [%0], {%1, %2};" :: "r"(dst + p * 512), "f"(v.x), "f"(v.y) : "memory");
          }
          __syncwarp();
          if (el) { mbar_arrive_local(bar_stat); PROFT(192 + l * 2 + hw); }
        }
        if (l & 1) {
          if (hw) bar_sync<BAR_KV + 1, 160>(); else bar_sync<BAR_KV, 160>();
          if (el) {
            if (hw == 0) PROFT(166 + l * 8);
            float* kvg = g_kv[par][l >> 1];
            bulk_reduce_f32(kvg + (jj * 4 + hw * 2) * KVH, sbase + (7 + hw) * SLOT, SLOT);
            bulk_reduce_f32(kvg + 32 * KVH + (jj * 4 + hw * 2) * 64, sbase + 10 * SLOT + hw * 512, 512);
            bulk_commit_wait();
            signal_release(&g_flags.kvready[l >> 1][jj]);
            if (hw == 0) PROFT(167 + l * 8);
          }
        }
        __syncwarp();
        if (hw == 0) {
#pragma unroll 1
          for (int e = 0; e < 4; e++) {
            asm volatile("bar.sync %0, 288;" :: "r"(BAR_O + e) : "memory");
            if (el) {
              if (!(e & 1)) PROFT(161 + l * 8 + (e >> 1) * 3);
              tma_store_2d((e & 2) ? &tm_xo : &tm_o, sbase + ((e & 2) ? 10 : 4) * SLOT + e * SLOT, jj * 128 + (e & 1) * 64, mm * 128);
              if (!(e == 2 && l == NLAYERS - 1)) bulk_commit_wait();
              if (!(e & 1)) PROFT(208 + l * 2 + (e >> 1));
              if (e < 2) SIGNAL_TILE(&g_flags.oready[l][mm][e]);
              else if (l < NLAYERS - 1) SIGNAL_TILE(&g_flags.xready[l + 1][mm][e & 1]);
              if (!(e & 1)) PROFT(162 + l * 8 + (e >> 1) * 3);
            }
            __syncwarp();
          }
        } else {
          if (l == 0 && NLAYERS > 1) {
            bar_sync<BAR_WF, 288>();
            if (el) { signal_release(&g_flags.wfready[jj]); PROFT(204); }
            __syncwarp();
          }
          mbar_wait(bar_done, 1);
        }
      }
    }
    cluster_sync();
  } else {
    asm volatile("setmaxnreg.inc.sync.aligned.u32 232;");
    const int tid = threadIdx.x;
    const int wg = warp >> 2;
    const int g = lane >> 2, t = lane & 3;
    const int r0 = warp * 16;
    const uint32_t srowoff = (r0 + (lane & 15)) * 128;
    const uint32_t lsw = (lane & 7) << 4, lhi = (lane >> 4) << 4;
    const uint32_t pK0 = sbase + SLOT, pQ0 = sbase + 4 * SLOT, pV0 = sbase + 7 * SLOT, pX0 = sbase + OFF_X;
    cluster_wait();
    PROF(0);
    mbar_wait(bar_x0, 0);
#define LOAD_X() \
    _Pragma("unroll") for (int j = 0; j < 8; j++) { \
      uint32_t x0, x1, x2, x3; \
      ldsm_x4(pX0 + (j >> 2) * SLOT + srowoff + ((((uint32_t)(j & 3) << 5) + lhi) ^ lsw), x0, x1, x2, x3); \
      acc[j * 8 + 0] = bf_lo(x0); acc[j * 8 + 1] = bf_hi(x0); acc[j * 8 + 2] = bf_lo(x1); acc[j * 8 + 3] = bf_hi(x1); \
      acc[j * 8 + 4] = bf_lo(x2); acc[j * 8 + 5] = bf_hi(x2); acc[j * 8 + 6] = bf_lo(x3); acc[j * 8 + 7] = bf_hi(x3); \
    }

#pragma unroll 1
    for (int l = 0; l < NLAYERS; l++) {
      const uint32_t tag = ep1 * 4 + l;
      bar_wg(wg);
      PROF(1 + l * 16);
      float accq[64], acckv[128];
      ACC_DEF(accq, 64); ACC_DEF(acckv, 128);
      {
        uint32_t a = sbase + OFF_X + wg * 8192, bst = sbase;
#define QKV_STEP(SC0) { \
          const uint64_t da = make_desc(a, 16, 1024); \
          a += SLOT; if (a >= sbase + 14 * SLOT) a -= 5 * SLOT; else if (i >= 2 && a >= sbase + 12 * SLOT) a -= 3 * SLOT; \
          const uint64_t db = make_desc(bst, 8192, 1024); \
          bst += 3 * SLOT; if (bst == sbase + 9 * SLOT) bst = sbase; \
          mbar_wait(bar_full + i * 8, 0); \
          if (i == 0) PROF(2 + l * 16); \
          if (i == 2) PROF(3 + l * 16); \
          wgmma_fence(); \
          wgmma_n128<SC0>(accq, da, db); wgmma_n256<SC0>(acckv, da, db + 1024); \
          _Pragma("unroll") for (int k4 = 1; k4 < 4; k4++) { \
            wgmma_n128<1>(accq, da + k4 * 2, db + k4 * 128); \
            wgmma_n256<1>(acckv, da + k4 * 2, db + 1024 + k4 * 128); \
          } \
          wgmma_commit(); }
        { const int i = 0; QKV_STEP(0) }
#pragma unroll 1
        for (int i = 1; i < 16; i++) {
          QKV_STEP(1)
          wgmma_wait<1>();
          if (lane < 2) mbar_arrive_remote(bar_done + (i - 1) * 8, lane);
        }
        wgmma_wait<0>();
        ACC_FENCE(accq, 64); ACC_FENCE(acckv, 128);
        if (lane < 2) mbar_arrive_remote(bar_done + 15 * 8, lane);
      }
      PROF(4 + l * 16);
      mbar_wait(bar_stat, l & 1);
      const float2 st0_ = lds64f(sbase + OFF_ST + (r0 + g) * 8), st1_ = lds64f(sbase + OFF_ST + (r0 + g + 8) * 8);
      const float rs0 = st0_.x, nm0 = st0_.y, rs1 = st1_.x, nm1 = st1_.y;
      const uint32_t csa = sbase + OFF_CS + t * 16;
      const bool hsend = (warp == 7) && !(l & 1) && (mm < 15);
      uint4* hdst = g_halo + (size_t)(mm * 8 + jj) * 1024 + lane;
      mbar_wait(bar_done + 14 * 8, 0);
      STAGE_ACC_LN(acckv, 64, pV0, csa + 1024, 4, 1);
      PROF(5 + l * 16);

      if (!(l & 1)) {
        mbar_wait(bar_done + 15 * 8, 0);
        STAGE_ACC_LN(acckv, 0, pK0, csa + 512, 8, 0);
        if (warp == 3) bar_arrive<BAR_MID, 64>();
        STAGE_ACC_LN(accq, 0, pQ0, csa, 8, -1);
        bar_wg(wg);
        if (warp == 4) bar_sync<BAR_MID, 64>();
        PROF(6 + l * 16);
        const uint32_t halo = sbase + 10 * SLOT;
        if (warp == 0) {
          if (mm > 0) {
#pragma unroll 1
            for (int part = 1; part >= 0; part--) {
              const uint4* src = hdst - 8 * 1024 + part * 512;
              const uint32_t hd = halo + part * 4096 + srowoff;
              int it = 0;
              bool ok;
              do {
                uint4 v[16];
#pragma unroll
                for (int i = 0; i < 16; i++) v[i] = ld_ll(src + i * 32);
                uint32_t bad = 0;
#pragma unroll
                for (int i = 0; i < 16; i++) bad |= (v[i].y ^ tag) | (v[i].w ^ tag);
#pragma unroll
                for (int j = 0; j < 8; j++)
                  stsm_x4(hd + (j >> 2) * 2048 + ((((uint32_t)(j & 3) << 5) + lhi) ^ lsw), v[2 * j].x, v[2 * j].z, v[2 * j + 1].x, v[2 * j + 1].z);
                ok = __all_sync(0xffffffffu, bad == 0);
              } while (!ok && ++it < (1 << 16));
            }
          } else {
#pragma unroll 1
            for (int i = 0; i < 16; i++) sts128(halo + i * 512 + lane * 16, 0, 0, 0, 0);
            __syncwarp();
          }
          bar_arrive<BAR_HRECV, 64>();
        }
        PROF(7 + l * 16);
        const float sc = 0.17677669529663687f * LOG2E;
        const int e = g & 1;
        uint32_t vmaskA = 0, vmask0 = 0;
#pragma unroll
        for (int jb = 0; jb < 4; jb++) {
          const int c = jb * 8 + 2 * t + e;
          const int d0 = g + 16 - c, d1 = g + 24 - c;
          if (d0 >= 0 && d0 <= 14) { vmaskA |= 1u << jb; if (c >= 16) vmask0 |= 1u << jb; }
          if (d1 >= 0 && d1 <= 14) { vmaskA |= 16u << jb; if (c >= 16) vmask0 |= 16u << jb; }
        }
#pragma unroll 1
        for (int it = (warp == 0 ? 2 : 0); it < (warp < 2 ? 3 : 2); it++) {
          const int hp = (it < 2) ? it : warp;
          const int rb0 = (it < 2) ? r0 : 0;
          if (it == 2 && warp == 1) bar_sync<BAR_HRECV, 64>();
          const uint32_t vmask = (rb0 == 0 && mm == 0) ? vmask0 : vmaskA;
          const uint32_t qb = pQ0 + hp * SLOT + (rb0 + (lane & 15)) * 128;
          const uint32_t kb1 = pK0 + hp * SLOT + rb0 * 128, vb1 = pV0 + hp * SLOT + rb0 * 128;
          const uint32_t kb0 = rb0 ? kb1 - 2048 : halo + hp * 2048, vb0 = rb0 ? vb1 - 2048 : halo + 4096 + hp * 2048;
          uint32_t qa[2][2][4];
#pragma unroll
          for (int hh = 0; hh < 2; hh++)
#pragma unroll
            for (int ks = 0; ks < 2; ks++) ldsm_x4(qb + ((hh * 64 + ks * 32 + lhi) ^ lsw), qa[hh][ks][0], qa[hh][ks][1], qa[hh][ks][2], qa[hh][ks][3]);
          float s[2][4][4];
#pragma unroll
          for (int jb = 0; jb < 4; jb++) {
            const uint32_t ka = ((jb < 2) ? kb0 : kb1) + ((jb & 1) * 8 + (lane & 7)) * 128;
#pragma unroll
            for (int hh = 0; hh < 2; hh++) {
              uint32_t b0, b1, b2, b3;
              ldsm_x4(ka + ((hh * 64 + ((lane >> 3) << 4)) ^ lsw), b0, b1, b2, b3);
              s[hh][jb][0] = s[hh][jb][1] = s[hh][jb][2] = s[hh][jb][3] = 0.f;
              mma_bf16(s[hh][jb], qa[hh][0][0], qa[hh][0][1], qa[hh][0][2], qa[hh][0][3], b0, b1);
              mma_bf16(s[hh][jb], qa[hh][1][0], qa[hh][1][1], qa[hh][1][2], qa[hh][1][3], b2, b3);
            }
          }
          float v[2][2][4], mx[2][2], sum[2][2];
#pragma unroll
          for (int hh = 0; hh < 2; hh++) {
            mx[hh][0] = mx[hh][1] = -INFINITY;
#pragma unroll
            for (int jb = 0; jb < 4; jb++) {
              const float a0 = e ? s[hh][jb][1] : s[hh][jb][0];
              const float a1 = e ? s[hh][jb][3] : s[hh][jb][2];
              v[hh][0][jb] = (vmask >> jb) & 1 ? a0 : -INFINITY;
              v[hh][1][jb] = (vmask >> (4 + jb)) & 1 ? a1 : -INFINITY;
              mx[hh][0] = fmaxf(mx[hh][0], v[hh][0][jb]); mx[hh][1] = fmaxf(mx[hh][1], v[hh][1][jb]);
            }
          }
#pragma unroll
          for (int o = 1; o <= 2; o <<= 1)
#pragma unroll
            for (int hh = 0; hh < 2; hh++)
#pragma unroll
              for (int r = 0; r < 2; r++) mx[hh][r] = fmaxf(mx[hh][r], __shfl_xor_sync(0xffffffffu, mx[hh][r], o));
#pragma unroll
          for (int hh = 0; hh < 2; hh++)
#pragma unroll
            for (int r = 0; r < 2; r++) {
              const float nb = -mx[hh][r] * sc;
              sum[hh][r] = 0.f;
#pragma unroll
              for (int jb = 0; jb < 4; jb++) { v[hh][r][jb] = ex2(fmaf(v[hh][r][jb], sc, nb)); sum[hh][r] += v[hh][r][jb]; }
            }
#pragma unroll
          for (int o = 1; o <= 2; o <<= 1)
#pragma unroll
            for (int hh = 0; hh < 2; hh++)
#pragma unroll
              for (int r = 0; r < 2; r++) sum[hh][r] += __shfl_xor_sync(0xffffffffu, sum[hh][r], o);
          const uint32_t esh = e * 16;
          float o[2][4][4];
#pragma unroll
          for (int hh = 0; hh < 2; hh++) {
            const float i0 = rcp_fast(sum[hh][0]), i1 = rcp_fast(sum[hh][1]);
#pragma unroll
            for (int dj = 0; dj < 4; dj++) { o[hh][dj][0] = o[hh][dj][1] = o[hh][dj][2] = o[hh][dj][3] = 0.f; }
#pragma unroll
            for (int ks = 0; ks < 2; ks++) {
              const uint32_t pa0 = pack_bf16(v[hh][0][2 * ks] * i0, 0.f) << esh, pa1 = pack_bf16(v[hh][1][2 * ks] * i1, 0.f) << esh;
              const uint32_t pa2 = pack_bf16(v[hh][0][2 * ks + 1] * i0, 0.f) << esh, pa3 = pack_bf16(v[hh][1][2 * ks + 1] * i1, 0.f) << esh;
              const uint32_t va = (ks ? vb1 : vb0) + (lane & 15) * 128;
#pragma unroll
              for (int dp = 0; dp < 2; dp++) {
                uint32_t b0, b1, b2, b3;
                ldsm_x4_t(va + ((hh * 64 + dp * 32 + lhi) ^ lsw), b0, b1, b2, b3);
                mma_bf16(o[hh][dp * 2], pa0, pa1, pa2, pa3, b0, b1);
                mma_bf16(o[hh][dp * 2 + 1], pa0, pa1, pa2, pa3, b2, b3);
              }
            }
          }
#pragma unroll
          for (int hh = 0; hh < 2; hh++)
#pragma unroll
            for (int dp = 0; dp < 2; dp++)
              stsm_x4(qb + ((hh * 64 + dp * 32 + lhi) ^ lsw), pack_bf16(o[hh][dp * 2][0], o[hh][dp * 2][1]), pack_bf16(o[hh][dp * 2][2], o[hh][dp * 2][3]),
                      pack_bf16(o[hh][dp * 2 + 1][0], o[hh][dp * 2 + 1][1]), pack_bf16(o[hh][dp * 2 + 1][2], o[hh][dp * 2 + 1][3]));
          if (hp == 0) { fence_proxy_async_smem(); bar_arrive<BAR_O, 288>(); }
        }
      } else {
        const float c0 = rs0 * LOG2E, c1 = rs1 * LOG2E;
        float p[2][4][4];
        PHI_LOAD(acckv, 0, csa + 512);
#pragma unroll 1
        for (int it = 0; it < 4; it++) {
          const uint32_t dst0 = ((it & 1) ? pQ0 : pK0) + srowoff, dst1 = dst0 + SLOT;
          float mx[2][2], mn[2][2];
#pragma unroll
          for (int hh = 0; hh < 2; hh++) {
            float mx0 = p[hh][0][0], mn0 = p[hh][0][0], mx1 = p[hh][0][2], mn1 = p[hh][0][2];
#pragma unroll
            for (int j = 0; j < 4; j++) {
              mx0 = fmaxf(mx0, fmaxf(p[hh][j][0], p[hh][j][1])); mn0 = fminf(mn0, fminf(p[hh][j][0], p[hh][j][1]));
              mx1 = fmaxf(mx1, fmaxf(p[hh][j][2], p[hh][j][3])); mn1 = fminf(mn1, fminf(p[hh][j][2], p[hh][j][3]));
            }
            mx[hh][0] = mx0; mx[hh][1] = mx1; mn[hh][0] = mn0; mn[hh][1] = mn1;
          }
#pragma unroll
          for (int o = 1; o <= 2; o <<= 1)
#pragma unroll
            for (int hh = 0; hh < 2; hh++)
#pragma unroll
              for (int r = 0; r < 2; r++) {
                mx[hh][r] = fmaxf(mx[hh][r], __shfl_xor_sync(0xffffffffu, mx[hh][r], o));
                mn[hh][r] = fminf(mn[hh][r], __shfl_xor_sync(0xffffffffu, mn[hh][r], o));
              }
          float en[2][4][4];
          float sp[2][2], sn[2][2];
#pragma unroll
          for (int hh = 0; hh < 2; hh++) {
            const float x0 = -mx[hh][0] * c0, x1 = -mx[hh][1] * c1, n0 = mn[hh][0] * c0, n1 = mn[hh][1] * c1;
            float sp0 = 0.f, sn0 = 0.f, sp1 = 0.f, sn1 = 0.f;
#pragma unroll
            for (int j = 0; j < 4; j++) {
              en[hh][j][0] = ex2(fmaf(p[hh][j][0], -c0, n0)); en[hh][j][1] = ex2(fmaf(p[hh][j][1], -c0, n0));
              en[hh][j][2] = ex2(fmaf(p[hh][j][2], -c1, n1)); en[hh][j][3] = ex2(fmaf(p[hh][j][3], -c1, n1));
              p[hh][j][0] = ex2(fmaf(p[hh][j][0], c0, x0)); p[hh][j][1] = ex2(fmaf(p[hh][j][1], c0, x0));
              p[hh][j][2] = ex2(fmaf(p[hh][j][2], c1, x1)); p[hh][j][3] = ex2(fmaf(p[hh][j][3], c1, x1));
              sp0 += p[hh][j][0] + p[hh][j][1]; sp1 += p[hh][j][2] + p[hh][j][3];
              sn0 += en[hh][j][0] + en[hh][j][1]; sn1 += en[hh][j][2] + en[hh][j][3];
            }
            sp[hh][0] = sp0; sp[hh][1] = sp1; sn[hh][0] = sn0; sn[hh][1] = sn1;
          }
#pragma unroll
          for (int o = 1; o <= 2; o <<= 1)
#pragma unroll
            for (int hh = 0; hh < 2; hh++)
#pragma unroll
              for (int r = 0; r < 2; r++) {
                sp[hh][r] += __shfl_xor_sync(0xffffffffu, sp[hh][r], o);
                sn[hh][r] += __shfl_xor_sync(0xffffffffu, sn[hh][r], o);
              }
          if (it == 0) mbar_wait(bar_done + 15 * 8, 0);
          if (it == 2) bar_sync<BAR_CONS, 256>();
#pragma unroll
          for (int hh = 0; hh < 2; hh++) {
            const float sp0 = rcp_fast(sp[hh][0]), sp1 = rcp_fast(sp[hh][1]), sn0 = rcp_fast(sn[hh][0]), sn1 = rcp_fast(sn[hh][1]);
            const uint32_t dst = hh ? dst1 : dst0;
#pragma unroll
            for (int ks = 0; ks < 2; ks++) {
              stsm_x4(dst + ((ks * 32 + lhi) ^ lsw),
                      pack_bf16(p[hh][2 * ks][0] * sp0, p[hh][2 * ks][1] * sp0), pack_bf16(p[hh][2 * ks][2] * sp1, p[hh][2 * ks][3] * sp1),
                      pack_bf16(p[hh][2 * ks + 1][0] * sp0, p[hh][2 * ks + 1][1] * sp0), pack_bf16(p[hh][2 * ks + 1][2] * sp1, p[hh][2 * ks + 1][3] * sp1));
              stsm_x4(dst + ((64 + ks * 32 + lhi) ^ lsw),
                      pack_bf16(en[hh][2 * ks][0] * sn0, en[hh][2 * ks][1] * sn0), pack_bf16(en[hh][2 * ks][2] * sn1, en[hh][2 * ks][3] * sn1),
                      pack_bf16(en[hh][2 * ks + 1][0] * sn0, en[hh][2 * ks + 1][1] * sn0), pack_bf16(en[hh][2 * ks + 1][2] * sn1, en[hh][2 * ks + 1][3] * sn1));
            }
          }
          if (it == 1) {
            fence_proxy_async_smem();
            bar_sync<BAR_CONS, 256>();
            PROF(6 + l * 16);
            float kv0[16], kv1[16], z0[4], z1[4];
            ACC_DEF(kv0, 16); ACC_DEF(kv1, 16); ACC_DEF(z0, 4); ACC_DEF(z1, 4);
            const uint64_t dp0 = make_desc(wg ? pQ0 : pK0, 16, 1024), dp1 = dp0 + 1024;
            const uint64_t dv = make_desc(pV0 + wg * SLOT, 16, 1024);
            const uint64_t d1 = (uint64_t)(((sbase + OFF_ONES) & 0x3FFFF) >> 4);
            wgmma_fence();
#pragma unroll
            for (int ks = 0; ks < 8; ks++) {
              if (ks == 0) {
                wgmma_n32_tt<0>(kv0, dp0, dv); wgmma_n32_tt<0>(kv1, dp1, dv + 4); wgmma_n8_tt<0>(z0, dp0, d1); wgmma_n8_tt<0>(z1, dp1, d1);
              } else {
                wgmma_n32_tt<1>(kv0, dp0 + ks * 128, dv + ks * 128);
                wgmma_n32_tt<1>(kv1, dp1 + ks * 128, dv + 4 + ks * 128);
                wgmma_n8_tt<1>(z0, dp0 + ks * 128, d1);
                wgmma_n8_tt<1>(z1, dp1 + ks * 128, d1);
              }
            }
            wgmma_commit();
            wgmma_wait<0>();
            ACC_FENCE(kv0, 16); ACC_FENCE(kv1, 16); ACC_FENCE(z0, 4); ACC_FENCE(z1, 4);
            PROF(70 + l);
            bar_wg(wg);
            const uint32_t rp = pV0 + wg * SLOT + ((t >> 1) * 64 + (warp & 3) * 16 + g) * 16 + (t & 1) * 8;
#pragma unroll
            for (int i = 0; i < 4; i++) {
              sts64f(rp + i * 2048, kv0[i * 4], kv0[i * 4 + 1]); sts64f(rp + i * 2048 + 128, kv0[i * 4 + 2], kv0[i * 4 + 3]);
              sts64f(rp + 8192 + i * 2048, kv1[i * 4], kv1[i * 4 + 1]); sts64f(rp + 8192 + i * 2048 + 128, kv1[i * 4 + 2], kv1[i * 4 + 3]);
            }
            {
              const float zv = (t == 0) ? z0[0] : (t == 1) ? z0[2] : (t == 2) ? z1[0] : z1[2];
              asm volatile("st.shared.f32 [%0], %1;" :: "r"(sbase + 10 * SLOT + wg * 512 + (t >> 1) * 256 + ((warp & 3) * 16 + (t & 1) * 8 + g) * 4), "f"(zv) : "memory");
            }
            fence_proxy_async_smem();
            if (wg) bar_arrive<BAR_KV + 1, 160>(); else bar_arrive<BAR_KV, 160>();
            PROF(7 + l * 16);
          }
          if (it == 0) { PHI_LOAD(acckv, 32, csa + 768); }
          else if (it == 1) { PHI_LOAD(accq, 0, csa); }
          else if (it == 2) { PHI_LOAD(accq, 32, csa + 256); }
        }
        PROF(8 + l * 16);
        {
          if (lane == 0) wait_flag(&g_flags.kvready[l >> 1][jj], ep1 * 32);
          __syncwarp();
          PROF(9 + l * 16);
          const int f = tid & 63, h = tid >> 6;
          const float* kvg = g_kv[par][l >> 1];
          const float4* src = reinterpret_cast<const float4*>(kvg + (jj * 4 + h) * KVH) + f;
          float4 v[8];
#pragma unroll
          for (int i = 0; i < 8; i++) v[i] = __ldcg(src + i * 64);
          const float z = __ldcg(kvg + 32 * KVH + jj * 256 + tid);
          const uint32_t dst = pV0 + h * 8192 + f * 128;
#pragma unroll
          for (int c = 0; c < 4; c++)
            sts128(dst + ((c << 4) ^ lsw), pack_bf16(v[2 * c].x, v[2 * c].y), pack_bf16(v[2 * c].z, v[2 * c].w),
                   pack_bf16(v[2 * c + 1].x, v[2 * c + 1].y), pack_bf16(v[2 * c + 1].z, v[2 * c + 1].w));
          sts128(dst + (64u ^ lsw), pack_bf16(z, 0.f), 0, 0, 0);
        }
        fence_proxy_async_smem();
        bar_sync<BAR_CONS, 256>();
        PROF(10 + l * 16);
        float o[4][20];
        ACC_DEF(o[0], 20); ACC_DEF(o[1], 20); ACC_DEF(o[2], 20); ACC_DEF(o[3], 20);
        wgmma_fence();
#pragma unroll
        for (int h = 0; h < 4; h++) {
          const uint64_t da = make_desc((h < 2 ? pK0 : pQ0) + (h & 1) * SLOT + wg * 8192, 16, 1024);
          const uint64_t db = make_desc(pV0 + h * 8192, 16, 1024);
#pragma unroll
          for (int ks = 0; ks < 4; ks++) { if (ks == 0) wgmma_n40<0>(o[h], da, db); else wgmma_n40<1>(o[h], da + ks * 2, db + ks * 128); }
        }
        wgmma_commit();
        wgmma_wait<0>();
        ACC_FENCE(o[0], 20); ACC_FENCE(o[1], 20); ACC_FENCE(o[2], 20); ACC_FENCE(o[3], 20);
        bar_wg(wg);
#pragma unroll
        for (int h = 0; h < 4; h++) {
          const float i0 = rcp_fast(__shfl_sync(0xffffffffu, o[h][16], lane & ~3) + 1e-6f);
          const float i1 = rcp_fast(__shfl_sync(0xffffffffu, o[h][18], lane & ~3) + 1e-6f);
          const uint32_t ob = pQ0 + (h >> 1) * SLOT + srowoff;
#pragma unroll
          for (int dp = 0; dp < 2; dp++)
            stsm_x4(ob + (((h & 1) * 64 + dp * 32 + lhi) ^ lsw),
                    pack_bf16(o[h][dp * 8 + 0] * i0, o[h][dp * 8 + 1] * i0), pack_bf16(o[h][dp * 8 + 2] * i1, o[h][dp * 8 + 3] * i1),
                    pack_bf16(o[h][dp * 8 + 4] * i0, o[h][dp * 8 + 5] * i0), pack_bf16(o[h][dp * 8 + 6] * i1, o[h][dp * 8 + 7] * i1));
          if (h == 1) { fence_proxy_async_smem(); bar_arrive<BAR_O, 288>(); }
        }
      }
      fence_proxy_async_smem();
      bar_arrive<BAR_O1, 288>();
      if (lane < 2) mbar_arrive_remote(bar_epi, lane);
      PROF(11 + l * 16);
      {
        float acc[64];
        LOAD_X();
        ACC_FENCE(acc, 64);
        bar_wg(wg);
#pragma unroll 1
        for (int s = 0; s < 16; s++) {
          const uint64_t da = make_desc(sbase + (uint32_t)((WO_ASLOT >> (4 * s)) & 15) * SLOT + wg * 8192, 16, 1024);
          const uint64_t db = make_desc(sbase + (uint32_t)((WO_BSLOT >> (4 * s)) & 15) * SLOT, 8192, 1024);
          if (l == 0 && s == 2 && NLAYERS > 1) {
            PROF(74);
            const int hl = warp >> 1, part = warp & 1;
            const uint4* wp = reinterpret_cast<const uint4*>(prm.wB_qkv + (size_t)(mm * 64 + g) * 3072 + part * 1024 + jj * 128 + hl * 32) + t;
            const uint2* pp = reinterpret_cast<const uint2*>(prm.wB_phi + (jj * 4 + hl) * 1024 + t * 256) + g;
            uint2* op = reinterpret_cast<uint2*>(g_wfold + (size_t)(mm * 64 + 2 * t) * 2048 + part * 1024 + jj * 128 + hl * 32) + g;
            uint4 v[8];
            uint2 x[8];
#pragma unroll
            for (int i = 0; i < 8; i++) x[i] = __ldcg(pp + i * 8);
#pragma unroll
            for (int i = 0; i < 8; i++) v[i] = __ldcg(wp + i * (8 * 384));
            uint32_t af[4][4];
#pragma unroll
            for (int e = 0; e < 4; e++) {
              af[e][0] = __byte_perm(x[2 * e].x, x[2 * e + 1].x, 0x5410); af[e][1] = __byte_perm(x[2 * e].x, x[2 * e + 1].x, 0x7632);
              af[e][2] = __byte_perm(x[2 * e].y, x[2 * e + 1].y, 0x5410); af[e][3] = __byte_perm(x[2 * e].y, x[2 * e + 1].y, 0x7632);
            }
#pragma unroll
            for (int i = 0; i < 8; i++) {
              float c0[4] = {0.f, 0.f, 0.f, 0.f}, c1[4] = {0.f, 0.f, 0.f, 0.f};
              mma_bf16(c0, af[0][0], af[0][1], af[1][0], af[1][1], v[i].x, v[i].y);
              mma_bf16(c1, af[0][2], af[0][3], af[1][2], af[1][3], v[i].x, v[i].y);
              mma_bf16(c0, af[2][0], af[2][1], af[3][0], af[3][1], v[i].z, v[i].w);
              mma_bf16(c1, af[2][2], af[2][3], af[3][2], af[3][3], v[i].z, v[i].w);
              op[i * 4096] = make_uint2(pack_bf16(c0[0], c0[2]), pack_bf16(c1[0], c1[2]));
              op[i * 4096 + 512] = make_uint2(pack_bf16(c0[1], c0[3]), pack_bf16(c1[1], c1[3]));
            }
            PROF(75);
            bar_arrive<BAR_WF, 288>();
          }
          mbar_wait(bar_full + s * 8, 1);
          if (s == 0) PROF(12 + l * 16);
          if (s == 2) PROF(13 + l * 16);
          wgmma_fence();
#pragma unroll
          for (int k4 = 0; k4 < 4; k4++) wgmma_n128<1>(acc, da + k4 * 2, db + k4 * 128);
          wgmma_commit();
          if (s > 0) { wgmma_wait<1>(); if (lane < 2) mbar_arrive_remote(bar_done + (s - 1) * 8, lane); }
        }
        wgmma_wait<0>();
        ACC_FENCE(acc, 64);
        if (lane < 2) mbar_arrive_remote(bar_done + 15 * 8, lane);
        PROF(14 + l * 16);
#pragma unroll
        for (int j = 0; j < 8; j++) {
          stsm_x4(pX0 + (j >> 2) * SLOT + srowoff + ((((uint32_t)(j & 3) << 5) + lhi) ^ lsw),
                  pack_bf16(acc[j * 8 + 0], acc[j * 8 + 1]), pack_bf16(acc[j * 8 + 2], acc[j * 8 + 3]),
                  pack_bf16(acc[j * 8 + 4], acc[j * 8 + 5]), pack_bf16(acc[j * 8 + 6], acc[j * 8 + 7]));
          if (j == 3) { fence_proxy_async_smem(); bar_arrive<BAR_X, 288>(); }
        }
        fence_proxy_async_smem();
        bar_arrive<BAR_X1, 288>();
        PROF(15 + l * 16);
      }
    }
    if (tid == 0) {
      unsigned old = atomicAdd(&g_flags.done, 1);
      if (old == ep1 * NMAIN - 1) {
        asm volatile("st.relaxed.gpu.global.u32 [%0], %1;" :: "l"(&g_flags.epoch), "r"(ep1) : "memory");
      }
    }
    __syncwarp();
    cluster_sync();
  }
}

typedef CUresult (*PFN_encode)(CUtensorMap*, CUtensorMapDataType, cuuint32_t, void*, const cuuint64_t*, const cuuint64_t*,
                               const cuuint32_t*, const cuuint32_t*, CUtensorMapInterleave, CUtensorMapSwizzle,
                               CUtensorMapL2promotion, CUtensorMapFloatOOBfill);

CUtensorMap make_map(PFN_encode enc, const void* ptr, uint64_t inner, uint64_t outer, uint32_t box_inner, uint32_t box_outer) {
  CUtensorMap m;
  cuuint64_t dims[2] = {inner, outer};
  cuuint64_t strides[1] = {inner * 2};
  cuuint32_t box[2] = {box_inner, box_outer};
  cuuint32_t es[2] = {1, 1};
  enc(&m, CU_TENSOR_MAP_DATA_TYPE_BFLOAT16, 2, const_cast<void*>(ptr), dims, strides, box, es, CU_TENSOR_MAP_INTERLEAVE_NONE,
      CU_TENSOR_MAP_SWIZZLE_128B, CU_TENSOR_MAP_L2_PROMOTION_L2_256B, CU_TENSOR_MAP_FLOAT_OOB_FILL_NONE);
  return m;
}

}

extern "C" void kernel_launch(void* const* d_in, const int* in_sizes, int n_in, void* d_out, int out_size) {
  (void)in_sizes; (void)n_in; (void)out_size;
  static PFN_encode enc = nullptr;
  if (!enc) {
    void* fn = nullptr;
    cudaDriverEntryPointQueryResult qr;
    cudaGetDriverEntryPoint("cuTensorMapEncodeTiled", &fn, cudaEnableDefault, &qr);
    enc = (PFN_encode)fn;
    cudaFuncSetAttribute(mega_kernel, cudaFuncAttributeMaxDynamicSharedMemorySize, SMEM_BYTES);
  }
  Params prm;
  prm.wA_qkv = (const __nv_bfloat16*)d_in[1];
  prm.wA_o = (const __nv_bfloat16*)d_in[2];
  prm.wB_qkv = (const __nv_bfloat16*)d_in[4];
  prm.wB_phi = (const __nv_bfloat16*)d_in[5];
  prm.wB_o = (const __nv_bfloat16*)d_in[6];
  prm.out = (__nv_bfloat16*)d_out;
  void *obuf = nullptr, *wf = nullptr;
  cudaGetSymbolAddress(&obuf, g_obuf);
  cudaGetSymbolAddress(&wf, g_wfold);
  CUtensorMap tm_x0 = make_map(enc, d_in[0], D_MODEL, S_LEN, 64, 128);
  CUtensorMap tm_xo = make_map(enc, d_out, D_MODEL, S_LEN, 64, 128);
  CUtensorMap tm_o = make_map(enc, obuf, D_MODEL, S_LEN, 64, 128);
  CUtensorMap tm_wf = make_map(enc, wf, 2048, D_MODEL, 64, 64);
  CUtensorMap tm_wqA = make_map(enc, d_in[1], 3 * D_MODEL, D_MODEL, 64, 64);
  CUtensorMap tm_wqB = make_map(enc, prm.wB_qkv, 3 * D_MODEL, D_MODEL, 64, 64);
  CUtensorMap tm_woA = make_map(enc, prm.wA_o, D_MODEL, D_MODEL, 64, 64);
  CUtensorMap tm_woB = make_map(enc, prm.wB_o, D_MODEL, D_MODEL, 64, 64);
  mega_kernel<<<NMAIN + NAUX, 384, SMEM_BYTES>>>(tm_x0, tm_xo, tm_o, tm_wf, tm_wqA, tm_wqB, tm_woA, tm_woB, prm);
}
```

```cpp
#include <cuda_runtime.h>
#include <cuda.h>
#include <cuda_bf16.h>
#include <stdint.h>

#define NLAYERS 4

namespace {

constexpr int S_LEN = 2048, D_MODEL = 1024;
constexpr int NAUX = 4, NMAIN = 128;
constexpr int SLOT = 16384;
constexpr int OFF_X = 12 * SLOT;
constexpr int OFF_BAR = 14 * SLOT;
constexpr int OFF_ONES = OFF_BAR + 384;
constexpr int OFF_ST = OFF_BAR + 512;
constexpr int OFF_CS = OFF_ST + 1024;
constexpr int SMEM_BYTES = OFF_CS + 1536;
constexpr unsigned long long WO_ASLOT = 0x8754218754218754ull;
constexpr unsigned long long WO_BSLOT = 0xA9B630A9B630A9B6ull;
__device__ __forceinline__ int kslice(int j, int i) { return i < 2 ? 2 * j + i : (i < 9 ? 2 * ((j + i - 1) & 7) : 2 * ((j + i) & 7) + 1); }
constexpr int KVH = 5 * 128 * 4;

struct Flags {
  unsigned xready[4][16][2];
  unsigned oready[4][16][2];
  unsigned kvready[2][8];
  unsigned csready[2];
  unsigned wfready[8];
  unsigned done;
  unsigned epoch;
  unsigned error;
};

__device__ Flags g_flags;
__device__ __nv_bfloat16 g_obuf[S_LEN * D_MODEL];
__device__ __nv_bfloat16 g_wfold[D_MODEL * 2048];
__device__ uint4 g_halo[16 * 8 * 512];
__device__ float g_kv[2][32 * KVH];
__device__ float g_colsum[2][3072];
__device__ uint4 g_stats[S_LEN * 8];

#define PROFT(i) do {} while (0)
#define PROF(i) do {} while (0)

__device__ __forceinline__ uint32_t smem_u32(const void* p) { return (uint32_t)__cvta_generic_to_shared(p); }
__device__ __forceinline__ bool elect_one() {
  uint32_t p;
  asm volatile("{\n.reg .pred p;\nelect.sync _|p, 0xffffffff;\nselp.u32 %0, 1, 0, p;\n}\n" : "=r"(p));
  return p != 0;
}
__device__ __forceinline__ void mbar_init(uint32_t bar, uint32_t cnt) {
  asm volatile("mbarrier.init.shared::cta.b64 [%0], %1;" :: "r"(bar), "r"(cnt));
}
__device__ __forceinline__ void mbar_expect_tx(uint32_t bar, uint32_t bytes) {
  asm volatile("mbarrier.arrive.expect_tx.shared::cta.b64 _, [%0], %1;" :: "r"(bar), "r"(bytes) : "memory");
}
__device__ __forceinline__ void mbar_wait(uint32_t bar, uint32_t parity) {
  uint32_t ok;
  int it = 0;
  do {
    asm volatile("{\n.reg .pred p;\nmbarrier.try_wait.parity.shared::cta.b64 p, [%1], %2;\nselp.u32 %0, 1, 0, p;\n}\n"
                 : "=r"(ok) : "r"(bar), "r"(parity) : "memory");
  } while (!ok && ++it < (1 << 20));
}
__device__ __forceinline__ void mbar_wait_sl(uint32_t bar, uint32_t parity) {
  uint32_t ok;
  int it = 0;
  do {
    asm volatile("{\n.reg .pred p;\nmbarrier.try_wait.parity.shared::cta.b64 p, [%1], %2, %3;\nselp.u32 %0, 1, 0, p;\n}\n"
                 : "=r"(ok) : "r"(bar), "r"(parity), "r"(20000) : "memory");
  } while (!ok && ++it < (1 << 16));
}
__device__ __forceinline__ void mbar_arrive_local(uint32_t bar) {
  asm volatile("mbarrier.arrive.shared::cta.b64 _, [%0];" :: "r"(bar) : "memory");
}
__device__ __forceinline__ void mbar_arrive_remote(uint32_t bar, uint32_t cta_rank) {
  asm volatile("{\n.reg .b32 ra;\nmapa.shared::cluster.u32 ra, %0, %1;\nmbarrier.arrive.shared::cluster.b64 _, [ra];\n}\n"
               :: "r"(bar), "r"(cta_rank) : "memory");
}
__device__ __forceinline__ void tma_load_2d(uint32_t dst, const CUtensorMap* tm, uint32_t bar, int c0, int c1) {
  asm volatile("cp.async.bulk.tensor.2d.shared::cluster.global.mbarrier::complete_tx::bytes [%0], [%1, {%3, %4}], [%2];"
               :: "r"(dst), "l"(tm), "r"(bar), "r"(c0), "r"(c1) : "memory");
}
__device__ __forceinline__ void tma_load_2d_mc(uint32_t dst, const CUtensorMap* tm, uint32_t bar, int c0, int c1) {
  asm volatile("cp.async.bulk.tensor.2d.shared::cluster.global.mbarrier::complete_tx::bytes.multicast::cluster [%0], [%1, {%3, %4}], [%2], %5;"
               :: "r"(dst), "l"(tm), "r"(bar), "r"(c0), "r"(c1), "h"((uint16_t)3) : "memory");
}
__device__ __forceinline__ void tma_store_2d(const CUtensorMap* tm, uint32_t src, int c0, int c1) {
  asm volatile("cp.async.bulk.tensor.2d.global.shared::cta.bulk_group [%0, {%2, %3}], [%1];"
               :: "l"(tm), "r"(src), "r"(c0), "r"(c1) : "memory");
}
__device__ __forceinline__ void bulk_commit_wait() {
  asm volatile("cp.async.bulk.commit_group;\ncp.async.bulk.wait_group 0;" ::: "memory");
}
__device__ __forceinline__ void prefetch_l2(const void* p, uint32_t bytes) {
  asm volatile("cp.async.bulk.prefetch.L2.global [%0], %1;" :: "l"(p), "r"(bytes) : "memory");
}
__device__ __forceinline__ void prefetch_tmap(const CUtensorMap* tm) {
  asm volatile("prefetch.tensormap [%0];" :: "l"(tm) : "memory");
}
__device__ __forceinline__ void fence_proxy_async_global() { asm volatile("fence.proxy.async.global;" ::: "memory"); }
__device__ __forceinline__ void fence_proxy_async_smem() { asm volatile("fence.proxy.async.shared::cta;" ::: "memory"); }
__device__ __forceinline__ void wait_flag(const unsigned* p, unsigned target) {
  unsigned v;
  int it = 0;
  do {
    asm volatile("ld.acquire.gpu.global.u32 %0, [%1];" : "=r"(v) : "l"(p) : "memory");
  } while ((int)(v - target) < 0 && ++it < (1 << 20));
}
__device__ __forceinline__ void signal_release(unsigned* p) {
  asm volatile("red.release.gpu.global.add.u32 [%0], 1;" :: "l"(p) : "memory");
}
__device__ __forceinline__ void signal_relaxed(unsigned* p) {
  asm volatile("red.relaxed.gpu.global.add.u32 [%0], 1;" :: "l"(p) : "memory");
}
#define SIGNAL_TILE signal_release
template <int ID, int N> __device__ __forceinline__ void bar_arrive() { asm volatile("bar.arrive %0, %1;" :: "n"(ID), "n"(N) : "memory"); }
template <int ID, int N> __device__ __forceinline__ void bar_sync() { asm volatile("bar.sync %0, %1;" :: "n"(ID), "n"(N) : "memory"); }
__device__ __forceinline__ void bar_wg(int wg) { asm volatile("bar.sync %0, 128;" :: "r"(2 + wg) : "memory"); }
__device__ __forceinline__ void cluster_sync() {
  asm volatile("barrier.cluster.arrive.release.aligned;\nbarrier.cluster.wait.acquire.aligned;" ::: "memory");
}
__device__ __forceinline__ void cluster_wait() { asm volatile("barrier.cluster.wait.acquire.aligned;" ::: "memory"); }
enum { BAR_CONS = 1, BAR_KV = 4  , BAR_HRECV = 6, BAR_O = 7, BAR_O1 = 8, BAR_X = 9, BAR_X1 = 10, BAR_MID = 11, BAR_WF = 12, BAR_SKEW = 13 };

__device__ __forceinline__ void wgmma_fence() { asm volatile("wgmma.fence.sync.aligned;" ::: "memory"); }
__device__ __forceinline__ void wgmma_commit() { asm volatile("wgmma.commit_group.sync.aligned;" ::: "memory"); }
template <int N> __device__ __forceinline__ void wgmma_wait() { asm volatile("wgmma.wait_group.sync.aligned %0;" :: "n"(N) : "memory"); }

#define ACC64_OUT(d) \
  "+f"(d[0]), "+f"(d[1]), "+f"(d[2]), "+f"(d[3]), "+f"(d[4]), "+f"(d[5]), "+f"(d[6]), "+f"(d[7]), \
  "+f"(d[8]), "+f"(d[9]), "+f"(d[10]), "+f"(d[11]), "+f"(d[12]), "+f"(d[13]), "+f"(d[14]), "+f"(d[15]), \
  "+f"(d[16]), "+f"(d[17]), "+f"(d[18]), "+f"(d[19]), "+f"(d[20]), "+f"(d[21]), "+f"(d[22]), "+f"(d[23]), \
  "+f"(d[24]), "+f"(d[25]), "+f"(d[26]), "+f"(d[27]), "+f"(d[28]), "+f"(d[29]), "+f"(d[30]), "+f"(d[31]), \
  "+f"(d[32]), "+f"(d[33]), "+f"(d[34]), "+f"(d[35]), "+f"(d[36]), "+f"(d[37]), "+f"(d[38]), "+f"(d[39]), \
  "+f"(d[40]), "+f"(d[41]), "+f"(d[42]), "+f"(d[43]), "+f"(d[44]), "+f"(d[45]), "+f"(d[46]), "+f"(d[47]), \
  "+f"(d[48]), "+f"(d[49]), "+f"(d[50]), "+f"(d[51]), "+f"(d[52]), "+f"(d[53]), "+f"(d[54]), "+f"(d[55]), \
  "+f"(d[56]), "+f"(d[57]), "+f"(d[58]), "+f"(d[59]), "+f"(d[60]), "+f"(d[61]), "+f"(d[62]), "+f"(d[63])
#define ACC64_REGS \
  "{%0,%1,%2,%3,%4,%5,%6,%7,%8,%9,%10,%11,%12,%13,%14,%15,%16,%17,%18,%19,%20,%21,%22,%23,%24,%25,%26,%27,%28,%29,%30,%31," \
  "%32,%33,%34,%35,%36,%37,%38,%39,%40,%41,%42,%43,%44,%45,%46,%47,%48,%49,%50,%51,%52,%53,%54,%55,%56,%57,%58,%59,%60,%61,%62,%63}"

template <int scale_d> __device__ __forceinline__ void wgmma_n128(float (&d)[64], uint64_t descA, uint64_t descB) {
  asm volatile("{\n.reg .pred p;\nsetp.ne.b32 p, %66, 0;\n"
               "wgmma.mma_async.sync.aligned.m64n128k16.f32.bf16.bf16 " ACC64_REGS ", %64, %65, p, 1, 1, 0, 1;\n}\n"
               : ACC64_OUT(d) : "l"(descA), "l"(descB), "n"(scale_d));
}
template <int scale_d> __device__ __forceinline__ void wgmma_n256(float (&d)[128], uint64_t descA, uint64_t descB) {
  asm volatile("{\n.reg .pred p;\nsetp.ne.b32 p, %130, 0;\n"
               "wgmma.mma_async.sync.aligned.m64n256k16.f32.bf16.bf16 {%0,%1,%2,%3,%4,%5,%6,%7,%8,%9,%10,%11,%12,%13,%14,%15,%16,%17,%18,%19,%20,%21,%22,%23,%24,%25,%26,%27,%28,%29,%30,%31,%32,%33,%34,%35,%36,%37,%38,%39,%40,%41,%42,%43,%44,%45,%46,%47,%48,%49,%50,%51,%52,%53,%54,%55,%56,%57,%58,%59,%60,%61,%62,%63,%64,%65,%66,%67,%68,%69,%70,%71,%72,%73,%74,%75,%76,%77,%78,%79,%80,%81,%82,%83,%84,%85,%86,%87,%88,%89,%90,%91,%92,%93,%94,%95,%96,%97,%98,%99,%100,%101,%102,%103,%104,%105,%106,%107,%108,%109,%110,%111,%112,%113,%114,%115,%116,%117,%118,%119,%120,%121,%122,%123,%124,%125,%126,%127}, %128, %129, p, 1, 1, 0, 1;\n}\n"
               : "+f"(d[0]), "+f"(d[1]), "+f"(d[2]), "+f"(d[3]), "+f"(d[4]), "+f"(d[5]), "+f"(d[6]), "+f"(d[7]), "+f"(d[8]), "+f"(d[9]), "+f"(d[10]), "+f"(d[11]), "+f"(d[12]), "+f"(d[13]), "+f"(d[14]), "+f"(d[15]), "+f"(d[16]), "+f"(d[17]), "+f"(d[18]), "+f"(d[19]), "+f"(d[20]), "+f"(d[21]), "+f"(d[22]), "+f"(d[23]), "+f"(d[24]), "+f"(d[25]), "+f"(d[26]), "+f"(d[27]), "+f"(d[28]), "+f"(d[29]), "+f"(d[30]), "+f"(d[31]), "+f"(d[32]), "+f"(d[33]), "+f"(d[34]), "+f"(d[35]), "+f"(d[36]), "+f"(d[37]), "+f"(d[38]), "+f"(d[39]), "+f"(d[40]), "+f"(d[41]), "+f"(d[42]), "+f"(d[43]), "+f"(d[44]), "+f"(d[45]), "+f"(d[46]), "+f"(d[47]), "+f"(d[48]), "+f"(d[49]), "+f"(d[50]), "+f"(d[51]), "+f"(d[52]), "+f"(d[53]), "+f"(d[54]), "+f"(d[55]), "+f"(d[56]), "+f"(d[57]), "+f"(d[58]), "+f"(d[59]), "+f"(d[60]), "+f"(d[61]), "+f"(d[62]), "+f"(d[63]), "+f"(d[64]), "+f"(d[65]), "+f"(d[66]), "+f"(d[67]), "+f"(d[68]), "+f"(d[69]), "+f"(d[70]), "+f"(d[71]), "+f"(d[72]), "+f"(d[73]), "+f"(d[74]), "+f"(d[75]), "+f"(d[76]), "+f"(d[77]), "+f"(d[78]), "+f"(d[79]), "+f"(d[80]), "+f"(d[81]), "+f"(d[82]), "+f"(d[83]), "+f"(d[84]), "+f"(d[85]), "+f"(d[86]), "+f"(d[87]), "+f"(d[88]), "+f"(d[89]), "+f"(d[90]), "+f"(d[91]), "+f"(d[92]), "+f"(d[93]), "+f"(d[94]), "+f"(d[95]), "+f"(d[96]), "+f"(d[97]), "+f"(d[98]), "+f"(d[99]), "+f"(d[100]), "+f"(d[101]), "+f"(d[102]), "+f"(d[103]), "+f"(d[104]), "+f"(d[105]), "+f"(d[106]), "+f"(d[107]), "+f"(d[108]), "+f"(d[109]), "+f"(d[110]), "+f"(d[111]), "+f"(d[112]), "+f"(d[113]), "+f"(d[114]), "+f"(d[115]), "+f"(d[116]), "+f"(d[117]), "+f"(d[118]), "+f"(d[119]), "+f"(d[120]), "+f"(d[121]), "+f"(d[122]), "+f"(d[123]), "+f"(d[124]), "+f"(d[125]), "+f"(d[126]), "+f"(d[127])
               : "l"(descA), "l"(descB), "n"(scale_d));
}
template <int scale_d> __device__ __forceinline__ void wgmma_n32_tt(float (&d)[16], uint64_t descA, uint64_t descB) {
  asm volatile("{\n.reg .pred p;\nsetp.ne.b32 p, %18, 0;\n"
               "wgmma.mma_async.sync.aligned.m64n32k16.f32.bf16.bf16 {%0,%1,%2,%3,%4,%5,%6,%7,%8,%9,%10,%11,%12,%13,%14,%15}, %16, %17, p, 1, 1, 1, 1;\n}\n"
               : "+f"(d[0]), "+f"(d[1]), "+f"(d[2]), "+f"(d[3]), "+f"(d[4]), "+f"(d[5]), "+f"(d[6]), "+f"(d[7]),
                 "+f"(d[8]), "+f"(d[9]), "+f"(d[10]), "+f"(d[11]), "+f"(d[12]), "+f"(d[13]), "+f"(d[14]), "+f"(d[15])
               : "l"(descA), "l"(descB), "n"(scale_d));
}
template <int scale_d> __device__ __forceinline__ void wgmma_n8_tt(float (&d)[4], uint64_t descA, uint64_t descB) {
  asm volatile("{\n.reg .pred p;\nsetp.ne.b32 p, %6, 0;\n"
               "wgmma.mma_async.sync.aligned.m64n8k16.f32.bf16.bf16 {%0,%1,%2,%3}, %4, %5, p, 1, 1, 1, 1;\n}\n"
               : "+f"(d[0]), "+f"(d[1]), "+f"(d[2]), "+f"(d[3]) : "l"(descA), "l"(descB), "n"(scale_d));
}
template <int scale_d> __device__ __forceinline__ void wgmma_n40(float (&d)[20], uint64_t descA, uint64_t descB) {
  asm volatile("{\n.reg .pred p;\nsetp.ne.b32 p, %22, 0;\n"
               "wgmma.mma_async.sync.aligned.m64n40k16.f32.bf16.bf16 {%0,%1,%2,%3,%4,%5,%6,%7,%8,%9,%10,%11,%12,%13,%14,%15,%16,%17,%18,%19}, %20, %21, p, 1, 1, 0, 1;\n}\n"
               : "+f"(d[0]), "+f"(d[1]), "+f"(d[2]), "+f"(d[3]), "+f"(d[4]), "+f"(d[5]), "+f"(d[6]), "+f"(d[7]),
                 "+f"(d[8]), "+f"(d[9]), "+f"(d[10]), "+f"(d[11]), "+f"(d[12]), "+f"(d[13]), "+f"(d[14]), "+f"(d[15]),
                 "+f"(d[16]), "+f"(d[17]), "+f"(d[18]), "+f"(d[19])
               : "l"(descA), "l"(descB), "n"(scale_d));
}
__device__ __forceinline__ uint64_t make_desc(uint32_t addr, uint32_t lbo_bytes, uint32_t sbo_bytes) {
  return (uint64_t)((addr & 0x3FFFF) >> 4) | ((uint64_t)(lbo_bytes >> 4) << 16) | ((uint64_t)(sbo_bytes >> 4) << 32) | (1ull << 62);
}

__device__ __forceinline__ void ldsm_x4(uint32_t addr, uint32_t& r0, uint32_t& r1, uint32_t& r2, uint32_t& r3) {
  asm volatile("ldmatrix.sync.aligned.m8n8.x4.shared.b16 {%0,%1,%2,%3}, [%4];" : "=r"(r0), "=r"(r1), "=r"(r2), "=r"(r3) : "r"(addr) : "memory");
}
__device__ __forceinline__ void ldsm_x4_t(uint32_t addr, uint32_t& r0, uint32_t& r1, uint32_t& r2, uint32_t& r3) {
  asm volatile("ldmatrix.sync.aligned.m8n8.x4.trans.shared.b16 {%0,%1,%2,%3}, [%4];" : "=r"(r0), "=r"(r1), "=r"(r2), "=r"(r3) : "r"(addr) : "memory");
}
__device__ __forceinline__ void stsm_x4(uint32_t addr, uint32_t r0, uint32_t r1, uint32_t r2, uint32_t r3) {
  asm volatile("stmatrix.sync.aligned.m8n8.x4.shared.b16 [%0], {%1,%2,%3,%4};" :: "r"(addr), "r"(r0), "r"(r1), "r"(r2), "r"(r3) : "memory");
}
__device__ __forceinline__ uint4 lds128(uint32_t addr) {
  uint4 v;
  asm volatile("ld.shared.v4.u32 {%0,%1,%2,%3}, [%4];" : "=r"(v.x), "=r"(v.y), "=r"(v.z), "=r"(v.w) : "r"(addr) : "memory");
  return v;
}
__device__ __forceinline__ void sts128(uint32_t addr, uint32_t a, uint32_t b, uint32_t c, uint32_t d) {
  asm volatile("st.shared.v4.u32 [%0], {%1,%2,%3,%4};" :: "r"(addr), "r"(a), "r"(b), "r"(c), "r"(d) : "memory");
}
__device__ __forceinline__ float2 lds64f(uint32_t addr) {
  float2 v;
  asm volatile("ld.shared.v2.f32 {%0,%1}, [%2];" : "=f"(v.x), "=f"(v.y) : "r"(addr) : "memory");
  return v;
}
__device__ __forceinline__ void sts64f(uint32_t addr, float a, float b) {
  asm volatile("st.shared.v2.f32 [%0], {%1,%2};" :: "r"(addr), "f"(a), "f"(b) : "memory");
}
__device__ __forceinline__ float4 lds128f(uint32_t addr) {
  float4 v;
  asm volatile("ld.shared.v4.f32 {%0,%1,%2,%3}, [%4];" : "=f"(v.x), "=f"(v.y), "=f"(v.z), "=f"(v.w) : "r"(addr) : "memory");
  return v;
}
__device__ __forceinline__ void mma_bf16(float (&c)[4], uint32_t a0, uint32_t a1, uint32_t a2, uint32_t a3, uint32_t b0, uint32_t b1) {
  asm("mma.sync.aligned.m16n8k16.row.col.f32.bf16.bf16.f32 {%0,%1,%2,%3}, {%4,%5,%6,%7}, {%8,%9}, {%0,%1,%2,%3};"
               : "+f"(c[0]), "+f"(c[1]), "+f"(c[2]), "+f"(c[3]) : "r"(a0), "r"(a1), "r"(a2), "r"(a3), "r"(b0), "r"(b1));
}
__device__ __forceinline__ uint32_t movm_t(uint32_t v) {
  uint32_t r;
  asm volatile("movmatrix.sync.aligned.m8n8.trans.b16 %0, %1;" : "=r"(r) : "r"(v));
  return r;
}
__device__ __forceinline__ uint32_t pack_bf16(float lo, float hi) {
  uint32_t r;
  asm("cvt.rn.bf16x2.f32 %0, %1, %2;" : "=r"(r) : "f"(hi), "f"(lo));
  return r;
}
__device__ __forceinline__ float bf_lo(uint32_t v) { return __uint_as_float(v << 16); }
__device__ __forceinline__ float bf_hi(uint32_t v) { return __uint_as_float(v & 0xFFFF0000u); }
__device__ __forceinline__ float ex2(float x) { float r; asm("ex2.approx.ftz.f32 %0, %1;" : "=f"(r) : "f"(x)); return r; }
__device__ __forceinline__ float rcp_fast(float x) { float r; asm("rcp.approx.ftz.f32 %0, %1;" : "=f"(r) : "f"(x)); return r; }
__device__ __forceinline__ void red_v4(float* p, float a, float b, float c, float d) {
  asm volatile("red.global.add.v4.f32 [%0], {%1, %2, %3, %4};" :: "l"(p), "f"(a), "f"(b), "f"(c), "f"(d) : "memory");
}
__device__ __forceinline__ void red_v2(float* p, float a, float b) {
  asm volatile("red.global.add.v2.f32 [%0], {%1, %2};" :: "l"(p), "f"(a), "f"(b) : "memory");
}
__device__ __forceinline__ void red_f32(float* p, float a) {
  asm volatile("red.global.add.f32 [%0], %1;" :: "l"(p), "f"(a) : "memory");
}

__device__ __forceinline__ void st_ll(uint4* p, uint32_t d0, uint32_t d1, uint32_t tag) {
  asm volatile("{\n.reg .b64 a, b;\nmov.b64 a, {%1, %3};\nmov.b64 b, {%2, %3};\nst.relaxed.gpu.global.v2.b64 [%0], {a, b};\n}\n"
               :: "l"(p), "r"(d0), "r"(d1), "r"(tag) : "memory");
}
__device__ __forceinline__ uint4 ld_ll(const uint4* p) {
  uint4 v;
  asm volatile("{\n.reg .b64 a, b;\nld.relaxed.gpu.global.v2.b64 {a, b}, [%4];\nmov.b64 {%0, %1}, a;\nmov.b64 {%2, %3}, b;\n}\n"
               : "=r"(v.x), "=r"(v.y), "=r"(v.z), "=r"(v.w) : "l"(p) : "memory");
  return v;
}
__device__ __forceinline__ void st_b128(uint4* p, uint32_t a, uint32_t b, uint32_t c, uint32_t d) {
  asm volatile("{\n.reg .b128 v;\nmov.b128 v, {%1, %2, %3, %4};\nst.relaxed.gpu.global.b128 [%0], v;\n}\n" :: "l"(p), "r"(a), "r"(b), "r"(c), "r"(d) : "memory");
}
__device__ __forceinline__ uint4 ld_b128(const uint4* p) {
  uint4 v;
  asm volatile("{\n.reg .b128 v;\nld.relaxed.gpu.global.b128 v, [%4];\nmov.b128 {%0, %1, %2, %3}, v;\n}\n" : "=r"(v.x), "=r"(v.y), "=r"(v.z), "=r"(v.w) : "l"(p) : "memory");
  return v;
}
__device__ __forceinline__ void bulk_reduce_f32(float* dst, uint32_t src, uint32_t bytes) {
  asm volatile("cp.reduce.async.bulk.global.shared::cta.bulk_group.add.f32 [%0], [%1], %2;" :: "l"(dst), "r"(src), "r"(bytes) : "memory");
}

constexpr float LOG2E = 1.4426950408889634f;

struct Params {
  const __nv_bfloat16* wA_qkv;
  const __nv_bfloat16* wA_o;
  const __nv_bfloat16* wB_qkv;
  const __nv_bfloat16* wB_phi;
  const __nv_bfloat16* wB_o;
  __nv_bfloat16* out;
};

#define ACC_DEF(d, n) _Pragma("unroll") for (int i_ = 0; i_ < (n); i_++) asm volatile("" : "=f"(d[i_]))
#define ACC_FENCE(d, n) _Pragma("unroll") for (int i_ = 0; i_ < (n); i_++) asm volatile("" : "+f"(d[i_]) :: "memory")

#define STAGE_ACC_LN(acc, off, p0, csa, NB, SENDP) \
  _Pragma("unroll") for (int b_ = 0; b_ < 8; b_ += (NB)) { \
    float4 c_[NB]; \
    uint32_t w_[NB][4]; \
    _Pragma("unroll") for (int j_ = 0; j_ < (NB); j_++) c_[j_] = lds128f((csa) + (b_ + j_) * 64); \
    _Pragma("unroll") for (int j_ = 0; j_ < (NB); j_++) { \
      const int o_ = (off) + (b_ + j_) * 8; \
      w_[j_][0] = pack_bf16(rs0 * fmaf(nm0, c_[j_].x, acc[o_ + 0]), rs0 * fmaf(nm0, c_[j_].y, acc[o_ + 1])); \
      w_[j_][1] = pack_bf16(rs1 * fmaf(nm1, c_[j_].x, acc[o_ + 2]), rs1 * fmaf(nm1, c_[j_].y, acc[o_ + 3])); \
      w_[j_][2] = pack_bf16(rs0 * fmaf(nm0, c_[j_].z, acc[o_ + 4]), rs0 * fmaf(nm0, c_[j_].w, acc[o_ + 5])); \
      w_[j_][3] = pack_bf16(rs1 * fmaf(nm1, c_[j_].z, acc[o_ + 6]), rs1 * fmaf(nm1, c_[j_].w, acc[o_ + 7])); \
    } \
    if ((SENDP) >= 0 && hsend) { \
      _Pragma("unroll") for (int j_ = 0; j_ < (NB); j_++) { \
        w_[j_][0] = (w_[j_][0] & ~1u) | hbit; \
        st_b128(hdst + ((SENDP) * 8 + b_ + j_) * 32, w_[j_][0], w_[j_][1], w_[j_][2], w_[j_][3]); \
      } \
    } \
    if ((SENDP) == 0) mbar_wait(bar_done + 15 * 8, 0); \
    _Pragma("unroll") for (int j_ = 0; j_ < (NB); j_++) \
      stsm_x4((p0) + ((b_ + j_) >> 2) * SLOT + srowoff + ((((uint32_t)((b_ + j_) & 3) << 5) + lhi) ^ lsw), w_[j_][0], w_[j_][1], w_[j_][2], w_[j_][3]); \
  }
#define PHI_LOAD(acc, csa) \
  _Pragma("unroll") for (int j_ = 0; j_ < 8; j_++) { \
    const float4 c_ = lds128f((csa) + j_ * 64); \
    p0[j_ * 4 + 0] = fmaf(nm0, c_.x, acc[j_ * 8 + 0]); p0[j_ * 4 + 1] = fmaf(nm0, c_.y, acc[j_ * 8 + 1]); \
    p0[j_ * 4 + 2] = fmaf(nm0, c_.z, acc[j_ * 8 + 4]); p0[j_ * 4 + 3] = fmaf(nm0, c_.w, acc[j_ * 8 + 5]); \
    p1[j_ * 4 + 0] = fmaf(nm1, c_.x, acc[j_ * 8 + 2]); p1[j_ * 4 + 1] = fmaf(nm1, c_.y, acc[j_ * 8 + 3]); \
    p1[j_ * 4 + 2] = fmaf(nm1, c_.z, acc[j_ * 8 + 6]); p1[j_ * 4 + 3] = fmaf(nm1, c_.w, acc[j_ * 8 + 7]); \
  }
__device__ __forceinline__ float rmax32(const float (&p)[32]) {
  float m[4];
#pragma unroll
  for (int j = 0; j < 4; j++) m[j] = fmaxf(p[j], p[j + 4]);
#pragma unroll
  for (int j = 8; j < 32; j++) m[j & 3] = fmaxf(m[j & 3], p[j]);
  return fmaxf(fmaxf(m[0], m[1]), fmaxf(m[2], m[3]));
}
__device__ __forceinline__ float rmin32(const float (&p)[32]) {
  float m[4];
#pragma unroll
  for (int j = 0; j < 4; j++) m[j] = fminf(p[j], p[j + 4]);
#pragma unroll
  for (int j = 8; j < 32; j++) m[j & 3] = fminf(m[j & 3], p[j]);
  return fminf(fminf(m[0], m[1]), fminf(m[2], m[3]));
}
__device__ __forceinline__ float exps32(float (&o)[32], const float (&p)[32], float c, float b) {
  float s[4] = {0.f, 0.f, 0.f, 0.f};
#pragma unroll
  for (int j = 0; j < 32; j++) { o[j] = ex2(fmaf(p[j], c, b)); s[j & 3] += o[j]; }
  return rcp_fast((s[0] + s[1]) + (s[2] + s[3]));
}
__device__ __forceinline__ void store32(const float (&e)[32], float inv, uint32_t dst, uint32_t dsw, int c0) {
#pragma unroll
  for (int j = 0; j < 4; j++)
    sts128(dst + (((c0 + j) << 4) ^ dsw), pack_bf16(e[j * 8] * inv, e[j * 8 + 1] * inv), pack_bf16(e[j * 8 + 2] * inv, e[j * 8 + 3] * inv),
           pack_bf16(e[j * 8 + 4] * inv, e[j * 8 + 5] * inv), pack_bf16(e[j * 8 + 6] * inv, e[j * 8 + 7] * inv));
}
#define SCHED_FENCE() asm volatile("pmevent 0;" ::: "memory")
#define PIN32(a) _Pragma("unroll") for (int i_ = 0; i_ < 32; i_++) asm volatile("" : "+f"((a)[i_]))

__global__ void __cluster_dims__(2, 1, 1) __launch_bounds__(384, 1)
mega_kernel(const __grid_constant__ CUtensorMap tm_x0, const __grid_constant__ CUtensorMap tm_xo,
            const __grid_constant__ CUtensorMap tm_o, const __grid_constant__ CUtensorMap tm_wf,
            const __grid_constant__ CUtensorMap tm_wqA, const __grid_constant__ CUtensorMap tm_wqB,
            const __grid_constant__ CUtensorMap tm_woA, const __grid_constant__ CUtensorMap tm_woB, const Params prm) {
  extern __shared__ __align__(1024) uint8_t smem_raw[];
  const uint32_t sbase = smem_u32(smem_raw);
  const uint32_t bar_full = sbase + OFF_BAR;
  const uint32_t bar_done = bar_full + 128;
  const uint32_t bar_stat = bar_full + 256, bar_epi = bar_full + 264, bar_x0 = bar_full + 272;

  const int warp = threadIdx.x >> 5, lane = threadIdx.x & 31;
  uint32_t rank;
  asm volatile("mov.u32 %0, %%cluster_ctarank;" : "=r"(rank));
  const int cta = (int)blockIdx.x - NAUX;
  const int cl = cta >> 1;
  const int jj = cl & 7, cc = cl >> 3;
  const int mm = cc * 2 + (int)rank;

  unsigned epoch;
  asm volatile("ld.relaxed.gpu.global.u32 %0, [%1];" : "=r"(epoch) : "l"(&g_flags.epoch) : "memory");
  const unsigned ep1 = epoch + 1;

  if (cta >= 0) {
    if (threadIdx.x == 0) {
      PROFT(79);
      for (int i = 0; i < 16; i++) { mbar_init(bar_full + i * 8, 1); mbar_init(bar_done + i * 8, 16); }
      mbar_init(bar_stat, 2); mbar_init(bar_epi, 16); mbar_init(bar_x0, 1);
      asm volatile("fence.mbarrier_init.release.cluster;" ::: "memory");
    }
    if (warp == 1) asm volatile("st.shared.u32 [%0], %1;" :: "r"(sbase + OFF_ONES + lane * 4), "r"(0x3F803F80u) : "memory");
    __syncthreads();
    asm volatile("barrier.cluster.arrive.relaxed.aligned;" ::: "memory");
  }

  if (cta < 0) {
    const int w = blockIdx.x * 12 + warp;
    const uint32_t buf = sbase + warp * SLOT, bar = sbase + OFF_BAR + warp * 16;
    const uint32_t lsw = (lane & 7) << 4, lhi = (lane >> 4) << 4, lrow = (lane & 15) * 128;
    const bool el = elect_one();
    if (el) {
      mbar_init(bar, 1); mbar_init(bar + 8, 1);
      asm volatile("fence.mbarrier_init.release.cluster;" ::: "memory");
    }
#pragma unroll 1
    for (int ph = 0; ph < (NLAYERS > 1 ? 2 : 1); ph++) {
      const CUtensorMap* tm = ph ? (w < 32 ? &tm_wf : &tm_wqB) : &tm_wqA;
      if (el) {
        if (ph && w < 32) { wait_flag(&g_flags.wfready[(w & 15) >> 1], ep1 * 16); fence_proxy_async_global(); }
        for (int i = 0; i < 2; i++) { mbar_expect_tx(bar + i * 8, 8192); tma_load_2d(buf + i * 8192, tm, bar + i * 8, w * 64, i * 64); }
      }
      __syncwarp();
      float cs[8][4];
#pragma unroll
      for (int i = 0; i < 8; i++) cs[i][0] = cs[i][1] = cs[i][2] = cs[i][3] = 0.f;
#pragma unroll 1
      for (int n = 0; n < 16; n++) {
        const uint32_t tb = buf + (n & 1) * 8192 + lrow;
        mbar_wait(bar + (n & 1) * 8, (n >> 1) & 1);
#pragma unroll
        for (int i = 0; i < 16; i++) {
          uint32_t b0, b1, b2, b3;
          ldsm_x4_t(tb + (i >> 2) * 2048 + (((i & 3) * 32 + lhi) ^ lsw), b0, b1, b2, b3);
          mma_bf16(cs[2 * (i & 3)], 0x3F803F80u, 0x3F803F80u, 0x3F803F80u, 0x3F803F80u, b0, b1);
          mma_bf16(cs[2 * (i & 3) + 1], 0x3F803F80u, 0x3F803F80u, 0x3F803F80u, 0x3F803F80u, b2, b3);
        }
        __syncwarp();
        if (el && n < 14) { mbar_expect_tx(bar + (n & 1) * 8, 8192); tma_load_2d(buf + (n & 1) * 8192, tm, bar + (n & 1) * 8, w * 64, (n + 2) * 64); }
      }
      if (lane < 4) {
#pragma unroll
        for (int i = 0; i < 8; i++) *reinterpret_cast<float2*>(g_colsum[ph] + w * 64 + i * 8 + lane * 2) = make_float2(cs[i][0], cs[i][1]);
      }
      __syncwarp();
      if (el) {
        signal_release(&g_flags.csready[ph]);
      }
    }
  } else if (warp >= 8) {
    asm volatile("setmaxnreg.dec.sync.aligned.u32 40;");
    if (warp == 8) {
      const bool el = elect_one();
      if (el) prefetch_tmap(&tm_wqA);
      cluster_wait();
      if (el) {
        const int col = jj * 128 + (int)rank * 64;
#pragma unroll 1
        for (int l = 0; l < NLAYERS; l++) {
          const CUtensorMap* tqk = (l & 1) ? &tm_wf : &tm_wqA;
          const CUtensorMap* tv = (l & 1) ? &tm_wqB : &tm_wqA;
          const CUtensorMap* two = (l & 1) ? &tm_woB : &tm_woA;
          if (l == 1) { wait_flag(&g_flags.wfready[jj], ep1 * 16); fence_proxy_async_global(); }
          uint32_t dst = sbase + rank * 8192;
#pragma unroll 1
          for (int i = 0; i < 16; i++) {
            if (i >= 3) mbar_wait_sl(bar_done + (i - 3) * 8, 0);
            else if (l) mbar_wait_sl(bar_done + (11 + 2 * i) * 8, 1);
            const uint32_t fb = bar_full + i * 8;
            mbar_expect_tx(fb, (i < 2) ? 3 * SLOT : 4 * SLOT);
            const int kk = kslice(jj, i);
            tma_load_2d_mc(dst, tqk, fb, col, kk * 64);
            tma_load_2d_mc(dst + SLOT, tqk, fb, col + 1024, kk * 64);
            tma_load_2d_mc(dst + 2 * SLOT, tv, fb, col + 2048, kk * 64);
            dst += 3 * SLOT;
            if (dst >= sbase + 9 * SLOT) dst -= 9 * SLOT;
          }
#pragma unroll 1
          for (int n = 0; n < 16; n++) {
            const int s = (n < 6) ? ((0x342051 >> (4 * n)) & 15) : n;
            if (n >= 6) mbar_wait_sl(bar_done + (n - 6) * 8, 1);
            else if (n == 5) mbar_wait_sl(bar_epi, l & 1);
            else mbar_wait_sl(bar_done + (13 + (n >> 1)) * 8, 0);
            const uint32_t fb = bar_full + s * 8;
            mbar_expect_tx(fb, (s < 2) ? SLOT : 2 * SLOT);
            tma_load_2d_mc(sbase + rank * 8192 + (uint32_t)((WO_BSLOT >> (4 * s)) & 15) * SLOT, two, fb, col, kslice(jj, s) * 64);
          }
        }
      }
      __syncwarp();
    } else if (warp == 9) {
      const bool el = elect_one();
      if (el) {
        mbar_expect_tx(bar_x0, 2 * SLOT);
        tma_load_2d(sbase + OFF_X, &tm_x0, bar_x0, jj * 128, mm * 128);
        tma_load_2d(sbase + OFF_X + SLOT, &tm_x0, bar_x0, jj * 128 + 64, mm * 128);
      }
#pragma unroll 1
      for (int l = 0; l < NLAYERS; l++) {
        if (el) {
          const CUtensorMap* tx = l ? &tm_xo : &tm_x0;
          if (l) {
            mbar_wait_sl(bar_done + 15 * 8, 1);
            wait_flag(&g_flags.xready[l][mm][0], ep1 * 8);
            fence_proxy_async_global();
            PROFT(160 + l * 8);
          }
          uint32_t dst = sbase + 9 * SLOT;
#pragma unroll 1
          for (int i = 2; i < 16; i++) {
            if (i >= 5) mbar_wait_sl(bar_done + (i - 3) * 8, 0);
            if (i == 9 && l) { wait_flag(&g_flags.xready[l][mm][1], ep1 * 8); fence_proxy_async_global(); }
            tma_load_2d(dst, tx, bar_full + i * 8, kslice(jj, i) * 64, mm * 128);
            dst += SLOT;
            if (dst == sbase + 12 * SLOT) dst = sbase + 9 * SLOT;
          }
        }
        if (el) {
          mbar_wait_sl(bar_epi, l & 1);
          wait_flag(&g_flags.oready[l][mm][0], ep1 * 8);
          fence_proxy_async_global();
          PROFT(163 + l * 8);
#pragma unroll 1
          for (int s = 2; s < 16; s++) {
            if (s >= 6) mbar_wait_sl(bar_done + (s - 6) * 8, 1);
            if (s == 7) { wait_flag(&g_flags.oready[l][mm][1], ep1 * 8); fence_proxy_async_global(); }
            tma_load_2d(sbase + (uint32_t)((WO_ASLOT >> (4 * s)) & 15) * SLOT, &tm_o, bar_full + s * 8, kslice(jj, s) * 64, mm * 128);
          }
        }
      }
      __syncwarp();
      cluster_wait();
    } else {
      const int hw = warp - 10, ht = hw * 32 + lane;
      const bool el = elect_one();
      cluster_wait();
      mbar_wait_sl(bar_x0, 0);
      if (hw) {
#pragma unroll 1
        for (int b = 0; b < 2; b++) {
          float4* z = reinterpret_cast<float4*>(g_kv[b] + (jj * 4) * KVH + mm * (4 * KVH / 16)) + lane;
#pragma unroll
          for (int i = 0; i < 5; i++) z[i * 32] = make_float4(0.f, 0.f, 0.f, 0.f);
        }
      }
#pragma unroll 1
      for (int l = 0; l < NLAYERS; l++) {
        const uint32_t tag = ep1 * 4 + l;
        if (l) mbar_wait_sl(bar_done, 0);
#pragma unroll 1
        for (int rr = 0; rr < 2; rr++) {
          const uint32_t a = sbase + OFF_X + (hw * 64 + rr * 32 + lane) * 128, sw = (lane & 7) << 4;
          uint32_t w0;
          asm volatile("ld.shared.u32 %0, [%1];" : "=r"(w0) : "r"(a) : "memory");
          const float pv = bf_lo(w0);
          float s0 = 0.f, s1 = 0.f, q0 = 0.f, q1 = 0.f;
#pragma unroll 1
          for (int c = 0; c < 16; c += 4) {
            uint4 v[4];
#pragma unroll
            for (int i = 0; i < 4; i++) v[i] = lds128(a + (c >> 3) * SLOT + ((((c & 7) + i) << 4) ^ sw));
#pragma unroll
            for (int i = 0; i < 4; i++) {
              float d;
              d = bf_lo(v[i].x) - pv; s0 += d; q0 = fmaf(d, d, q0); d = bf_hi(v[i].x) - pv; s1 += d; q1 = fmaf(d, d, q1);
              d = bf_lo(v[i].y) - pv; s0 += d; q0 = fmaf(d, d, q0); d = bf_hi(v[i].y) - pv; s1 += d; q1 = fmaf(d, d, q1);
              d = bf_lo(v[i].z) - pv; s0 += d; q0 = fmaf(d, d, q0); d = bf_hi(v[i].z) - pv; s1 += d; q1 = fmaf(d, d, q1);
              d = bf_lo(v[i].w) - pv; s0 += d; q0 = fmaf(d, d, q0); d = bf_hi(v[i].w) - pv; s1 += d; q1 = fmaf(d, d, q1);
            }
          }
          s0 += s1; q0 += q1;
          const float mu = s0 * (1.f / 128.f);
          st_ll(g_stats + (size_t)(mm * 128 + hw * 64 + rr * 32 + lane) * 8 + jj, __float_as_uint(pv + mu), __float_as_uint(fmaf(-s0, mu, q0)), tag);
        }
        if (l == 0) {
          const char* wrow = reinterpret_cast<const char*>(prm.wB_qkv + (size_t)(mm * 64 + ht) * 3072 + jj * 128);
          prefetch_l2(wrow, 256); prefetch_l2(wrow + 2048, 256);
          if (ht == 63) prefetch_l2(prm.wB_phi + jj * 4096, 8192);
          if (ht < 16) prefetch_l2((const char*)((ht & 8) ? prm.wB_o : prm.wA_o) + (size_t)cta * 16384 + (ht & 7) * 2048, 2048);
        }
#pragma unroll 1
        for (int rr = 0; rr < 2; rr++) {
          const uint4* srow = g_stats + (size_t)(mm * 128 + hw * 64 + rr * 32 + lane) * 8;
          float sm[8], m2 = 0.f;
#pragma unroll
          for (int hf = 0; hf < 2; hf++) {
            uint32_t bad;
            int it = 0;
            float q;
            do {
              bad = 0; q = 0.f;
#pragma unroll
              for (int i = 0; i < 4; i++) {
                const uint4 v = ld_ll(srow + hf * 4 + i);
                sm[hf * 4 + i] = __uint_as_float(v.x); q += __uint_as_float(v.z);
                bad |= (v.y ^ tag) | (v.w ^ tag);
              }
            } while (bad && ++it < (1 << 18));
            m2 += q;
          }
          const float mean = (((sm[0] + sm[1]) + (sm[2] + sm[3])) + ((sm[4] + sm[5]) + (sm[6] + sm[7]))) * 0.125f;
          float dd = 0.f;
#pragma unroll
          for (int i = 0; i < 8; i++) { const float e = sm[i] - mean; dd = fmaf(e, e, dd); }
          const float rs = rsqrtf(fmaxf(fmaf(dd, 128.f, m2), 0.f) * (1.f / 1024.f) + 1e-5f);
          asm volatile("st.shared.v2.f32 [%0], {%1, %2};" :: "r"(sbase + OFF_ST + (hw * 64 + rr * 32 + lane) * 8), "f"(rs), "f"(-mean) : "memory");
        }
        {
          if (l < 2 && el) wait_flag(&g_flags.csready[l], ep1 * 48);
          __syncwarp();
          const float2* src = reinterpret_cast<const float2*>(g_colsum[l & 1] + jj * 128) + ht;
          const uint32_t dst = sbase + OFF_CS + (ht >> 3) * 64 + (ht & 3) * 16 + ((ht >> 2) & 1) * 8;
#pragma unroll
          for (int p = 0; p < 3; p++) {
            const float2 v = __ldcg(src + p * 512);
            asm volatile("st.shared.v2.f32 [%0], {%1, %2};" :: "r"(dst + p * 512), "f"(v.x), "f"(v.y) : "memory");
          }
          __syncwarp();
          if (el) { mbar_arrive_local(bar_stat); PROFT(192 + l * 2 + hw); }
        }
        if ((l & 1) && hw) {
          bar_sync<BAR_KV, 288>();
          if (el) { PROFT(166 + l * 8); signal_release(&g_flags.kvready[l >> 1][jj]); PROFT(167 + l * 8); }
        }
        __syncwarp();
        if (hw == 0) {
#pragma unroll 1
          for (int e = 0; e < 4; e++) {
            asm volatile("bar.sync %0, 288;" :: "r"(BAR_O + e) : "memory");
            if (el) {
              if (!(e & 1)) PROFT(161 + l * 8 + (e >> 1) * 3);
              tma_store_2d((e & 2) ? &tm_xo : &tm_o, sbase + ((e & 2) ? 10 : 4) * SLOT + e * SLOT, jj * 128 + (e & 1) * 64, mm * 128);
              if (!(e == 2 && l == NLAYERS - 1)) bulk_commit_wait();
              if (!(e & 1)) PROFT(208 + l * 2 + (e >> 1));
              if (e < 2) SIGNAL_TILE(&g_flags.oready[l][mm][e]);
              else if (l < NLAYERS - 1) SIGNAL_TILE(&g_flags.xready[l + 1][mm][e & 1]);
              if (!(e & 1)) PROFT(162 + l * 8 + (e >> 1) * 3);
            }
            __syncwarp();
          }
        } else {
          if (l == 0 && NLAYERS > 1) {
            bar_sync<BAR_WF, 288>();
            if (el) { signal_release(&g_flags.wfready[jj]); PROFT(204); }
            __syncwarp();
          }
          mbar_wait_sl(bar_done, 1);
        }
      }
    }
    cluster_sync();
  } else {
    asm volatile("setmaxnreg.inc.sync.aligned.u32 232;");
    const int tid = threadIdx.x;
    const int wg = warp >> 2;
    const int g = lane >> 2, t = lane & 3;
    const int r0 = warp * 16;
    const uint32_t srowoff = (r0 + (lane & 15)) * 128;
    const uint32_t lsw = (lane & 7) << 4, lhi = (lane >> 4) << 4;
    const uint32_t pK0 = sbase + SLOT, pQ0 = sbase + 4 * SLOT, pV0 = sbase + 7 * SLOT, pX0 = sbase + OFF_X;
    cluster_wait();
    PROF(0);
    mbar_wait(bar_x0, 0);
#define LOAD_X() \
    _Pragma("unroll") for (int j = 0; j < 8; j++) { \
      uint32_t x0, x1, x2, x3; \
      ldsm_x4(pX0 + (j >> 2) * SLOT + srowoff + ((((uint32_t)(j & 3) << 5) + lhi) ^ lsw), x0, x1, x2, x3); \
      acc[j * 8 + 0] = bf_lo(x0); acc[j * 8 + 1] = bf_hi(x0); acc[j * 8 + 2] = bf_lo(x1); acc[j * 8 + 3] = bf_hi(x1); \
      acc[j * 8 + 4] = bf_lo(x2); acc[j * 8 + 5] = bf_hi(x2); acc[j * 8 + 6] = bf_lo(x3); acc[j * 8 + 7] = bf_hi(x3); \
    }

#pragma unroll 1
    for (int l = 0; l < NLAYERS; l++) {
      bar_wg(wg);
      PROF(1 + l * 16);
      float accq[64], acckv[128];
      ACC_DEF(accq, 64); ACC_DEF(acckv, 128);
      {
        uint32_t a = sbase + OFF_X + wg * 8192, bst = sbase;
#define QKV_STEP(SC0) { \
          const uint64_t da = make_desc(a, 16, 1024); \
          a += SLOT; if (a >= sbase + 14 * SLOT) a -= 5 * SLOT; else if (i >= 2 && a >= sbase + 12 * SLOT) a -= 3 * SLOT; \
          const uint64_t db = make_desc(bst, 8192, 1024); \
          bst += 3 * SLOT; if (bst == sbase + 9 * SLOT) bst = sbase; \
          mbar_wait(bar_full + i * 8, 0); \
          if (i == 0) PROF(2 + l * 16); \
          if (i == 2) PROF(3 + l * 16); \
          if (i == 15 && wg == 0) bar_sync<BAR_SKEW, 256>(); \
          wgmma_fence(); \
          wgmma_n128<SC0>(accq, da, db); wgmma_n256<SC0>(acckv, da, db + 1024); \
          _Pragma("unroll") for (int k4 = 1; k4 < 4; k4++) { \
            wgmma_n128<1>(accq, da + k4 * 2, db + k4 * 128); \
            wgmma_n256<1>(acckv, da + k4 * 2, db + 1024 + k4 * 128); \
          } \
          wgmma_commit(); }
        { const int i = 0; QKV_STEP(0) }
#pragma unroll 1
        for (int i = 1; i < 16; i++) {
          QKV_STEP(1)
          if (i == 15 && wg == 1) bar_arrive<BAR_SKEW, 256>();
          wgmma_wait<1>();
          if (lane < 2) mbar_arrive_remote(bar_done + (i - 1) * 8, lane);
        }
      }
      mbar_wait(bar_stat, l & 1);
      const float2 st0_ = lds64f(sbase + OFF_ST + (r0 + g) * 8), st1_ = lds64f(sbase + OFF_ST + (r0 + g + 8) * 8);
      const float rs0 = st0_.x, nm0 = st0_.y, rs1 = st1_.x, nm1 = st1_.y;
      const uint32_t csa = sbase + OFF_CS + t * 16;
      const bool hsend = (warp == 7) && !(l & 1) && (mm < 15);
      uint4* hdst = g_halo + (size_t)(mm * 8 + jj) * 512 + lane;
      const uint32_t hbit = (NLAYERS > 2) ? (l == 0) : (ep1 & 1);
      mbar_wait(bar_done + 14 * 8, 0);
      wgmma_wait<0>();
      ACC_FENCE(accq, 64); ACC_FENCE(acckv, 128);
      if (lane < 2) mbar_arrive_remote(bar_done + 15 * 8, lane);
      PROF(4 + l * 16);
      STAGE_ACC_LN(acckv, 64, pV0, csa + 1024, 4, 1);
      PROF(5 + l * 16);

      if (!(l & 1)) {
        STAGE_ACC_LN(acckv, 0, pK0, csa + 512, 8, 0);
        if (warp == 3) bar_arrive<BAR_MID, 64>();
        STAGE_ACC_LN(accq, 0, pQ0, csa, 8, -1);
        bar_wg(wg);
        if (warp == 4) bar_sync<BAR_MID, 64>();
        PROF(6 + l * 16);
        const uint32_t halo = sbase + 10 * SLOT;
        if (warp == 0) {
          if (mm > 0) {
            int it = 0;
            bool ok;
            do {
              uint4 v[16];
#pragma unroll
              for (int i = 0; i < 16; i++) v[i] = ld_b128(hdst - 8 * 512 + i * 32);
              uint32_t bad = 0;
#pragma unroll
              for (int i = 0; i < 16; i++) {
                bad |= v[i].x ^ hbit;
                stsm_x4(halo + srowoff + (i >> 2) * 2048 + ((((uint32_t)(i & 3) << 5) + lhi) ^ lsw), v[i].x, v[i].y, v[i].z, v[i].w);
              }
              ok = __all_sync(0xffffffffu, (bad & 1) == 0);
            } while (!ok && ++it < (1 << 16));
          } else {
#pragma unroll 1
            for (int i = 0; i < 16; i++) sts128(halo + i * 512 + lane * 16, 0, 0, 0, 0);
            __syncwarp();
          }
          bar_arrive<BAR_HRECV, 64>();
        }
        PROF(7 + l * 16);
        const float sc = 0.17677669529663687f * LOG2E;
        const int e = g & 1;
        uint32_t vmaskA = 0, vmask0 = 0;
#pragma unroll
        for (int jb = 0; jb < 4; jb++) {
          const int c = jb * 8 + 2 * t + e;
          const int d0 = g + 16 - c, d1 = g + 24 - c;
          if (d0 >= 0 && d0 <= 14) { vmaskA |= 1u << jb; if (c >= 16) vmask0 |= 1u << jb; }
          if (d1 >= 0 && d1 <= 14) { vmaskA |= 16u << jb; if (c >= 16) vmask0 |= 16u << jb; }
        }
#pragma unroll 1
        for (int it = (warp == 0 ? 2 : 0); it < (warp < 2 ? 3 : 2); it++) {
          const int hp = (it < 2) ? it : warp;
          const int rb0 = (it < 2) ? r0 : 0;
          if (it == 2 && warp == 1) bar_sync<BAR_HRECV, 64>();
          const uint32_t vmask = (rb0 == 0 && mm == 0) ? vmask0 : vmaskA;
          const uint32_t qb = pQ0 + hp * SLOT + (rb0 + (lane & 15)) * 128;
          const uint32_t kb1 = pK0 + hp * SLOT + rb0 * 128, vb1 = pV0 + hp * SLOT + rb0 * 128;
          const uint32_t kb0 = rb0 ? kb1 - 2048 : halo + hp * 2048, vb0 = rb0 ? vb1 - 2048 : halo + 4096 + hp * 2048;
          uint32_t qa[2][2][4];
#pragma unroll
          for (int hh = 0; hh < 2; hh++)
#pragma unroll
            for (int ks = 0; ks < 2; ks++) ldsm_x4(qb + ((hh * 64 + ks * 32 + lhi) ^ lsw), qa[hh][ks][0], qa[hh][ks][1], qa[hh][ks][2], qa[hh][ks][3]);
          float s[2][4][4];
#pragma unroll
          for (int jb = 0; jb < 4; jb++) {
            const uint32_t ka = ((jb < 2) ? kb0 : kb1) + ((jb & 1) * 8 + (lane & 7)) * 128;
#pragma unroll
            for (int hh = 0; hh < 2; hh++) {
              uint32_t b0, b1, b2, b3;
              ldsm_x4(ka + ((hh * 64 + ((lane >> 3) << 4)) ^ lsw), b0, b1, b2, b3);
              s[hh][jb][0] = s[hh][jb][1] = s[hh][jb][2] = s[hh][jb][3] = 0.f;
              mma_bf16(s[hh][jb], qa[hh][0][0], qa[hh][0][1], qa[hh][0][2], qa[hh][0][3], b0, b1);
              mma_bf16(s[hh][jb], qa[hh][1][0], qa[hh][1][1], qa[hh][1][2], qa[hh][1][3], b2, b3);
            }
          }
          float v[2][2][4], mx[2][2], sum[2][2];
#pragma unroll
          for (int hh = 0; hh < 2; hh++) {
            mx[hh][0] = mx[hh][1] = -INFINITY;
#pragma unroll
            for (int jb = 0; jb < 4; jb++) {
              const float a0 = e ? s[hh][jb][1] : s[hh][jb][0];
              const float a1 = e ? s[hh][jb][3] : s[hh][jb][2];
              v[hh][0][jb] = (vmask >> jb) & 1 ? a0 : -INFINITY;
              v[hh][1][jb] = (vmask >> (4 + jb)) & 1 ? a1 : -INFINITY;
              mx[hh][0] = fmaxf(mx[hh][0], v[hh][0][jb]); mx[hh][1] = fmaxf(mx[hh][1], v[hh][1][jb]);
            }
          }
#pragma unroll
          for (int o = 1; o <= 2; o <<= 1)
#pragma unroll
            for (int hh = 0; hh < 2; hh++)
#pragma unroll
              for (int r = 0; r < 2; r++) mx[hh][r] = fmaxf(mx[hh][r], __shfl_xor_sync(0xffffffffu, mx[hh][r], o));
#pragma unroll
          for (int hh = 0; hh < 2; hh++)
#pragma unroll
            for (int r = 0; r < 2; r++) {
              const float nb = -mx[hh][r] * sc;
              sum[hh][r] = 0.f;
#pragma unroll
              for (int jb = 0; jb < 4; jb++) { v[hh][r][jb] = ex2(fmaf(v[hh][r][jb], sc, nb)); sum[hh][r] += v[hh][r][jb]; }
            }
#pragma unroll
          for (int o = 1; o <= 2; o <<= 1)
#pragma unroll
            for (int hh = 0; hh < 2; hh++)
#pragma unroll
              for (int r = 0; r < 2; r++) sum[hh][r] += __shfl_xor_sync(0xffffffffu, sum[hh][r], o);
          const uint32_t esh = e * 16;
          float o[2][4][4];
#pragma unroll
          for (int hh = 0; hh < 2; hh++) {
            const float i0 = rcp_fast(sum[hh][0]), i1 = rcp_fast(sum[hh][1]);
#pragma unroll
            for (int dj = 0; dj < 4; dj++) { o[hh][dj][0] = o[hh][dj][1] = o[hh][dj][2] = o[hh][dj][3] = 0.f; }
#pragma unroll
            for (int ks = 0; ks < 2; ks++) {
              const uint32_t pa0 = pack_bf16(v[hh][0][2 * ks] * i0, 0.f) << esh, pa1 = pack_bf16(v[hh][1][2 * ks] * i1, 0.f) << esh;
              const uint32_t pa2 = pack_bf16(v[hh][0][2 * ks + 1] * i0, 0.f) << esh, pa3 = pack_bf16(v[hh][1][2 * ks + 1] * i1, 0.f) << esh;
              const uint32_t va = (ks ? vb1 : vb0) + (lane & 15) * 128;
#pragma unroll
              for (int dp = 0; dp < 2; dp++) {
                uint32_t b0, b1, b2, b3;
                ldsm_x4_t(va + ((hh * 64 + dp * 32 + lhi) ^ lsw), b0, b1, b2, b3);
                mma_bf16(o[hh][dp * 2], pa0, pa1, pa2, pa3, b0, b1);
                mma_bf16(o[hh][dp * 2 + 1], pa0, pa1, pa2, pa3, b2, b3);
              }
            }
          }
#pragma unroll
          for (int hh = 0; hh < 2; hh++)
#pragma unroll
            for (int dp = 0; dp < 2; dp++)
              stsm_x4(qb + ((hh * 64 + dp * 32 + lhi) ^ lsw), pack_bf16(o[hh][dp * 2][0], o[hh][dp * 2][1]), pack_bf16(o[hh][dp * 2][2], o[hh][dp * 2][3]),
                      pack_bf16(o[hh][dp * 2 + 1][0], o[hh][dp * 2 + 1][1]), pack_bf16(o[hh][dp * 2 + 1][2], o[hh][dp * 2 + 1][3]));
          if (hp == 0) { fence_proxy_async_smem(); bar_arrive<BAR_O, 288>(); }
        }
      } else {
        float p0[32], p1[32];
        PHI_LOAD(acckv, csa + 512);
        float4* kvg = reinterpret_cast<float4*>(g_kv[l >> 1] + (jj * 4 + wg * 2) * KVH) + (tid & 127);
        const float c0 = rs0 * LOG2E, c1 = rs1 * LOG2E;
        const uint32_t dst = ((t & 2) ? pQ0 : pK0) + (t & 1) * SLOT + (r0 + g) * 128;
        const uint32_t dsw = (uint32_t)(g ^ (2 * t)) << 4;
#pragma unroll 1
        for (int it = 0; it < 2; it++) {
          float e[32];
          float mn0 = rmin32(p0);
          asm volatile("" : "+f"(mn0)); SCHED_FENCE();
          float ia = exps32(e, p0, -c0, mn0 * c0), mx0 = rmax32(p0), mn1 = rmin32(p1);
          asm volatile("" : "+f"(ia), "+f"(mx0), "+f"(mn1)); PIN32(e);
          if (it == 0) mbar_wait(bar_done + 15 * 8, 0);
          else bar_sync<BAR_CONS, 256>();
          SCHED_FENCE();
          store32(e, ia, dst, dsw, 4);
          float ib = exps32(p0, p0, c0, -mx0 * c0);
          asm volatile("" : "+f"(ib)); PIN32(p0); SCHED_FENCE();
          store32(p0, ib, dst, dsw, 0);
          float ic = exps32(e, p1, -c1, mn1 * c1), mx1 = rmax32(p1);
          asm volatile("" : "+f"(ic), "+f"(mx1)); PIN32(e); SCHED_FENCE();
          store32(e, ic, dst + 1024, dsw, 4);
          float id = exps32(p1, p1, c1, -mx1 * c1);
          asm volatile("" : "+f"(id)); PIN32(p1); SCHED_FENCE();
          store32(p1, id, dst + 1024, dsw, 0);
          if (it == 0) {
            fence_proxy_async_smem();
            bar_sync<BAR_CONS, 256>();
            PROF(6 + l * 16);
            float kv0[16], kv1[16], z0[4], z1[4];
            ACC_DEF(kv0, 16); ACC_DEF(kv1, 16); ACC_DEF(z0, 4); ACC_DEF(z1, 4);
            const uint64_t dp0 = make_desc(wg ? pQ0 : pK0, 16, 1024), dp1 = dp0 + 1024;
            const uint64_t dv = make_desc(pV0 + wg * SLOT, 16, 1024);
            const uint64_t d1 = (uint64_t)(((sbase + OFF_ONES) & 0x3FFFF) >> 4);
            wgmma_fence();
#pragma unroll
            for (int ks = 0; ks < 8; ks++) {
              if (ks == 0) { wgmma_n32_tt<0>(kv0, dp0, dv); wgmma_n8_tt<0>(z0, dp0, d1); }
              else { wgmma_n32_tt<1>(kv0, dp0 + ks * 128, dv + ks * 128); wgmma_n8_tt<1>(z0, dp0 + ks * 128, d1); }
            }
            wgmma_commit();
#pragma unroll
            for (int ks = 0; ks < 8; ks++) {
              if (ks == 0) { wgmma_n32_tt<0>(kv1, dp1, dv + 4); wgmma_n8_tt<0>(z1, dp1, d1); }
              else { wgmma_n32_tt<1>(kv1, dp1 + ks * 128, dv + 4 + ks * 128); wgmma_n8_tt<1>(z1, dp1 + ks * 128, d1); }
            }
            wgmma_commit();
            wgmma_wait<1>();
            ACC_FENCE(kv0, 16); ACC_FENCE(z0, 4);
#pragma unroll
            for (int i = 0; i < 4; i++) red_v4(reinterpret_cast<float*>(kvg + i * 128), kv0[i * 4], kv0[i * 4 + 1], kv0[i * 4 + 2], kv0[i * 4 + 3]);
            red_v4(reinterpret_cast<float*>(kvg + 512), z0[0], z0[1], z0[2], z0[3]);
            wgmma_wait<0>();
            ACC_FENCE(kv1, 16); ACC_FENCE(z1, 4);
            PROF(70 + l);
#pragma unroll
            for (int i = 0; i < 4; i++) red_v4(reinterpret_cast<float*>(kvg + 640 + i * 128), kv1[i * 4], kv1[i * 4 + 1], kv1[i * 4 + 2], kv1[i * 4 + 3]);
            red_v4(reinterpret_cast<float*>(kvg + 640 + 512), z1[0], z1[1], z1[2], z1[3]);
            bar_arrive<BAR_KV, 288>();
            PROF(7 + l * 16);
            PHI_LOAD(accq, csa);
          }
        }
        PROF(8 + l * 16);
        {
          if (lane == 0) wait_flag(&g_flags.kvready[l >> 1][jj], ep1 * 16);
          __syncwarp();
          PROF(9 + l * 16);
          float4 v[10];
#pragma unroll
          for (int i = 0; i < 10; i++) v[i] = __ldcg(kvg + i * 128);
          const uint32_t dst = pV0 + wg * SLOT + ((warp & 3) * 16 + (lane & 15)) * 128;
#pragma unroll
          for (int i = 0; i < 4; i++) {
            const float4 a = v[(i >> 1) * 5 + (i & 1) * 2], b = v[(i >> 1) * 5 + (i & 1) * 2 + 1];
            stsm_x4(dst + (i >> 1) * 8192 + (((i & 1) * 32 + lhi) ^ lsw), pack_bf16(a.x, a.y), pack_bf16(a.z, a.w), pack_bf16(b.x, b.y), pack_bf16(b.z, b.w));
          }
          stsm_x4(dst + (lane >> 4) * 8192 + (64u ^ lsw), pack_bf16(v[4].x, v[4].y), pack_bf16(v[4].z, v[4].w), pack_bf16(v[9].x, v[9].y), pack_bf16(v[9].z, v[9].w));
        }
        fence_proxy_async_smem();
        bar_sync<BAR_CONS, 256>();
        PROF(10 + l * 16);
        float o[4][20];
        ACC_DEF(o[0], 20); ACC_DEF(o[1], 20); ACC_DEF(o[2], 20); ACC_DEF(o[3], 20);
        wgmma_fence();
#pragma unroll
        for (int hh = 0; hh < 4; hh++) {
          const int h = hh ^ 2;
          const uint64_t da = make_desc((h < 2 ? pK0 : pQ0) + (h & 1) * SLOT + wg * 8192, 16, 1024);
          const uint64_t db = make_desc(pV0 + h * 8192, 16, 1024);
#pragma unroll
          for (int ks = 0; ks < 4; ks++) { if (ks == 0) wgmma_n40<0>(o[h], da, db); else wgmma_n40<1>(o[h], da + ks * 2, db + ks * 128); }
          if (hh & 1) wgmma_commit();
        }
        uint32_t ow[4][8];
#pragma unroll
        for (int hh = 0; hh < 4; hh++) {
          const int h = hh ^ 2;
          if (hh == 0) { wgmma_wait<1>(); ACC_FENCE(o[2], 20); ACC_FENCE(o[3], 20); }
          if (hh == 2) { bar_wg(wg); wgmma_wait<0>(); ACC_FENCE(o[0], 20); ACC_FENCE(o[1], 20); }
          const float i0 = rcp_fast(o[h][16] + 1e-6f), i1 = rcp_fast(o[h][18] + 1e-6f);
#pragma unroll
          for (int i = 0; i < 4; i++) {
            ow[h][2 * i] = pack_bf16(o[h][i * 4] * i0, o[h][i * 4 + 1] * i0);
            ow[h][2 * i + 1] = pack_bf16(o[h][i * 4 + 2] * i1, o[h][i * 4 + 3] * i1);
          }
        }
#pragma unroll
        for (int h = 0; h < 4; h++) {
          const uint32_t ob = pQ0 + (h >> 1) * SLOT + srowoff;
#pragma unroll
          for (int dp = 0; dp < 2; dp++)
            stsm_x4(ob + (((h & 1) * 64 + dp * 32 + lhi) ^ lsw), ow[h][dp * 4], ow[h][dp * 4 + 1], ow[h][dp * 4 + 2], ow[h][dp * 4 + 3]);
          if (h == 1) { fence_proxy_async_smem(); bar_arrive<BAR_O, 288>(); }
        }
      }
      fence_proxy_async_smem();
      bar_arrive<BAR_O1, 288>();
      if (lane < 2) mbar_arrive_remote(bar_epi, lane);
      PROF(11 + l * 16);
      {
        float acc[64];
        LOAD_X();
        ACC_FENCE(acc, 64);
        bar_wg(wg);
#pragma unroll 1
        for (int s = 0; s < 16; s++) {
          const uint64_t da = make_desc(sbase + (uint32_t)((WO_ASLOT >> (4 * s)) & 15) * SLOT + wg * 8192, 16, 1024);
          const uint64_t db = make_desc(sbase + (uint32_t)((WO_BSLOT >> (4 * s)) & 15) * SLOT, 8192, 1024);
          if (l == 0 && s == 2 && NLAYERS > 1) {
            PROF(74);
            const int part = warp & 1, rw = mm * 64 + (warp >> 1) * 16;
            const uint4* wp = reinterpret_cast<const uint4*>(prm.wB_qkv + (size_t)(rw + g) * 3072 + part * 1024 + jj * 128) + t;
            const uint2* pp = reinterpret_cast<const uint2*>(prm.wB_phi + jj * 4096 + t * 256) + g;
            uint4* op = reinterpret_cast<uint4*>(g_wfold + (size_t)(rw + 2 * t) * 2048 + part * 1024 + jj * 128) + 2 * g;
            uint4 v[8];
#pragma unroll
            for (int i = 0; i < 8; i++) v[i] = __ldcg(wp + (i >> 2) * (8 * 384) + (i & 3) * 4);
            uint32_t w[2][2][2][4];
#pragma unroll
            for (int h = 0; h < 4; h++) {
              uint32_t af[4][4];
#pragma unroll
              for (int e = 0; e < 4; e++) {
                const uint2 x = __ldg(pp + h * 256 + e * 16), y = __ldg(pp + h * 256 + e * 16 + 8);
                af[e][0] = __byte_perm(x.x, y.x, 0x5410); af[e][1] = __byte_perm(x.x, y.x, 0x7632);
                af[e][2] = __byte_perm(x.y, y.y, 0x5410); af[e][3] = __byte_perm(x.y, y.y, 0x7632);
              }
#pragma unroll
              for (int i = 0; i < 2; i++) {
                const uint4 b = v[i * 4 + h];
                float c0[4] = {0.f, 0.f, 0.f, 0.f}, c1[4] = {0.f, 0.f, 0.f, 0.f};
                mma_bf16(c0, af[0][0], af[0][1], af[1][0], af[1][1], b.x, b.y);
                mma_bf16(c1, af[0][2], af[0][3], af[1][2], af[1][3], b.x, b.y);
                mma_bf16(c0, af[2][0], af[2][1], af[3][0], af[3][1], b.z, b.w);
                mma_bf16(c1, af[2][2], af[2][3], af[3][2], af[3][3], b.z, b.w);
                w[i][0][0][h] = pack_bf16(c0[0], c0[2]); w[i][0][1][h] = pack_bf16(c1[0], c1[2]);
                w[i][1][0][h] = pack_bf16(c0[1], c0[3]); w[i][1][1][h] = pack_bf16(c1[1], c1[3]);
              }
            }
#pragma unroll
            for (int i = 0; i < 8; i++) {
              const uint32_t (&q)[4] = w[i >> 2][(i >> 1) & 1][i & 1];
              op[(i >> 2) * 2048 + ((i >> 1) & 1) * 256 + (i & 1)] = make_uint4(q[0], q[1], q[2], q[3]);
            }
            PROF(75);
            bar_arrive<BAR_WF, 288>();
          }
          mbar_wait(bar_full + s * 8, 1);
          if (s == 0) PROF(12 + l * 16);
          if (s == 2) PROF(13 + l * 16);
          wgmma_fence();
#pragma unroll
          for (int k4 = 0; k4 < 4; k4++) wgmma_n128<1>(acc, da + k4 * 2, db + k4 * 128);
          wgmma_commit();
          if (s > 0) { wgmma_wait<1>(); if (lane < 2) mbar_arrive_remote(bar_done + (s - 1) * 8, lane); }
        }
        wgmma_wait<0>();
        ACC_FENCE(acc, 64);
        if (lane < 2) mbar_arrive_remote(bar_done + 15 * 8, lane);
        PROF(14 + l * 16);
#pragma unroll
        for (int j = 0; j < 8; j++) {
          stsm_x4(pX0 + (j >> 2) * SLOT + srowoff + ((((uint32_t)(j & 3) << 5) + lhi) ^ lsw),
                  pack_bf16(acc[j * 8 + 0], acc[j * 8 + 1]), pack_bf16(acc[j * 8 + 2], acc[j * 8 + 3]),
                  pack_bf16(acc[j * 8 + 4], acc[j * 8 + 5]), pack_bf16(acc[j * 8 + 6], acc[j * 8 + 7]));
          if (j == 3) { fence_proxy_async_smem(); bar_arrive<BAR_X, 288>(); }
        }
        fence_proxy_async_smem();
        bar_arrive<BAR_X1, 288>();
        PROF(15 + l * 16);
      }
    }
    if (tid == 0) {
      unsigned old = atomicAdd(&g_flags.done, 1);
      if (old == ep1 * NMAIN - 1) {
        asm volatile("st.relaxed.gpu.global.u32 [%0], %1;" :: "l"(&g_flags.epoch), "r"(ep1) : "memory");
      }
    }
    __syncwarp();
    cluster_sync();
  }
}

typedef CUresult (*PFN_encode)(CUtensorMap*, CUtensorMapDataType, cuuint32_t, void*, const cuuint64_t*, const cuuint64_t*,
                               const cuuint32_t*, const cuuint32_t*, CUtensorMapInterleave, CUtensorMapSwizzle,
                               CUtensorMapL2promotion, CUtensorMapFloatOOBfill);

CUtensorMap make_map(PFN_encode enc, const void* ptr, uint64_t inner, uint64_t outer, uint32_t box_inner, uint32_t box_outer) {
  CUtensorMap m;
  cuuint64_t dims[2] = {inner, outer};
  cuuint64_t strides[1] = {inner * 2};
  cuuint32_t box[2] = {box_inner, box_outer};
  cuuint32_t es[2] = {1, 1};
  enc(&m, CU_TENSOR_MAP_DATA_TYPE_BFLOAT16, 2, const_cast<void*>(ptr), dims, strides, box, es, CU_TENSOR_MAP_INTERLEAVE_NONE,
      CU_TENSOR_MAP_SWIZZLE_128B, CU_TENSOR_MAP_L2_PROMOTION_L2_256B, CU_TENSOR_MAP_FLOAT_OOB_FILL_NONE);
  return m;
}

}

extern "C" void kernel_launch(void* const* d_in, const int* in_sizes, int n_in, void* d_out, int out_size) {
  (void)in_sizes; (void)n_in; (void)out_size;
  static PFN_encode enc = nullptr;
  if (!enc) {
    void* fn = nullptr;
    cudaDriverEntryPointQueryResult qr;
    cudaGetDriverEntryPoint("cuTensorMapEncodeTiled", &fn, cudaEnableDefault, &qr);
    enc = (PFN_encode)fn;
    cudaFuncSetAttribute(mega_kernel, cudaFuncAttributeMaxDynamicSharedMemorySize, SMEM_BYTES);
  }
  Params prm;
  prm.wA_qkv = (const __nv_bfloat16*)d_in[1];
  prm.wA_o = (const __nv_bfloat16*)d_in[2];
  prm.wB_qkv = (const __nv_bfloat16*)d_in[4];
  prm.wB_phi = (const __nv_bfloat16*)d_in[5];
  prm.wB_o = (const __nv_bfloat16*)d_in[6];
  prm.out = (__nv_bfloat16*)d_out;
  void *obuf = nullptr, *wf = nullptr;
  cudaGetSymbolAddress(&obuf, g_obuf);
  cudaGetSymbolAddress(&wf, g_wfold);
  CUtensorMap tm_x0 = make_map(enc, d_in[0], D_MODEL, S_LEN, 64, 128);
  CUtensorMap tm_xo = make_map(enc, d_out, D_MODEL, S_LEN, 64, 128);
  CUtensorMap tm_o = make_map(enc, obuf, D_MODEL, S_LEN, 64, 128);
  CUtensorMap tm_wf = make_map(enc, wf, 2048, D_MODEL, 64, 64);
  CUtensorMap tm_wqA = make_map(enc, d_in[1], 3 * D_MODEL, D_MODEL, 64, 64);
  CUtensorMap tm_wqB = make_map(enc, prm.wB_qkv, 3 * D_MODEL, D_MODEL, 64, 64);
  CUtensorMap tm_woA = make_map(enc, prm.wA_o, D_MODEL, D_MODEL, 64, 64);
  CUtensorMap tm_woB = make_map(enc, prm.wB_o, D_MODEL, D_MODEL, 64, 64);
  mega_kernel<<<NMAIN + NAUX, 384, SMEM_BYTES>>>(tm_x0, tm_xo, tm_o, tm_wf, tm_wqA, tm_wqB, tm_woA, tm_woB, prm);
}
```

```cpp
#include <cuda_runtime.h>
#include <cuda.h>
#include <cuda_bf16.h>
#include <stdint.h>

#define NLAYERS 4

#define STAG1 300
namespace {

constexpr int S_LEN = 2048, D_MODEL = 1024;
constexpr int NAUX = 4, NMAIN = 128;
constexpr int SLOT = 16384;
constexpr int OFF_X = 12 * SLOT;
constexpr int OFF_BAR = 14 * SLOT;
constexpr int OFF_ST = OFF_BAR + 512;
constexpr int OFF_CS = OFF_ST + 1024;
constexpr int SMEM_BYTES = OFF_CS + 1536;
constexpr unsigned long long WO_ASLOT = 0x8754218754218754ull;
constexpr unsigned long long WO_BSLOT = 0xA9B630A9B630A9B6ull;
__device__ __forceinline__ int kslice(int j, int i) { return i < 2 ? 2 * j + i : (i < 9 ? 2 * ((j + i - 1) & 7) : 2 * ((j + i) & 7) + 1); }
constexpr int KVH = 5 * 128 * 4;

struct __align__(128) Flag { unsigned v; unsigned pad[31]; };
struct Flags {
  Flag xready[4][16][2];
  Flag oready[4][16][2];
  Flag kvready[2][8];
  Flag wfready[8];
  Flag done;
  Flag epoch;
};

__device__ Flags g_flags;
__device__ __nv_bfloat16 g_obuf[S_LEN * D_MODEL];
__device__ __nv_bfloat16 g_wfold[D_MODEL * 2048];
__device__ uint4 g_halo[16 * 8 * 512];
__device__ float g_kv[2][32 * KVH];
__device__ uint4 g_colsum[2][1536];
__device__ uint4 g_stats[S_LEN * 8];

#define PROFT(i) do {} while (0)
#define PROF(i) do {} while (0)

__device__ __forceinline__ uint32_t smem_u32(const void* p) { return (uint32_t)__cvta_generic_to_shared(p); }
__device__ __forceinline__ bool elect_one() {
  uint32_t p;
  asm volatile("{\n.reg .pred p;\nelect.sync _|p, 0xffffffff;\nselp.u32 %0, 1, 0, p;\n}\n" : "=r"(p));
  return p != 0;
}
__device__ __forceinline__ void mbar_init(uint32_t bar, uint32_t cnt) {
  asm volatile("mbarrier.init.shared::cta.b64 [%0], %1;" :: "r"(bar), "r"(cnt));
}
__device__ __forceinline__ void mbar_expect_tx(uint32_t bar, uint32_t bytes) {
  asm volatile("mbarrier.arrive.expect_tx.shared::cta.b64 _, [%0], %1;" :: "r"(bar), "r"(bytes) : "memory");
}
__device__ __forceinline__ void mbar_wait(uint32_t bar, uint32_t parity) {
  uint32_t ok;
  int it = 0;
  do {
    asm volatile("{\n.reg .pred p;\nmbarrier.try_wait.parity.shared::cta.b64 p, [%1], %2;\nselp.u32 %0, 1, 0, p;\n}\n"
                 : "=r"(ok) : "r"(bar), "r"(parity) : "memory");
  } while (!ok && ++it < (1 << 20));
}
__device__ __forceinline__ void mbar_wait_sl(uint32_t bar, uint32_t parity) {
  uint32_t ok;
  int it = 0;
  do {
    asm volatile("{\n.reg .pred p;\nmbarrier.try_wait.parity.shared::cta.b64 p, [%1], %2, %3;\nselp.u32 %0, 1, 0, p;\n}\n"
                 : "=r"(ok) : "r"(bar), "r"(parity), "r"(20000) : "memory");
  } while (!ok && ++it < (1 << 16));
}
__device__ __forceinline__ void mbar_arrive_local(uint32_t bar) {
  asm volatile("mbarrier.arrive.shared::cta.b64 _, [%0];" :: "r"(bar) : "memory");
}
__device__ __forceinline__ void mbar_arrive_remote(uint32_t bar, uint32_t cta_rank) {
  asm volatile("{\n.reg .b32 ra;\nmapa.shared::cluster.u32 ra, %0, %1;\nmbarrier.arrive.shared::cluster.b64 _, [ra];\n}\n"
               :: "r"(bar), "r"(cta_rank) : "memory");
}
__device__ __forceinline__ void tma_load_2d(uint32_t dst, const CUtensorMap* tm, uint32_t bar, int c0, int c1) {
  asm volatile("cp.async.bulk.tensor.2d.shared::cluster.global.mbarrier::complete_tx::bytes [%0], [%1, {%3, %4}], [%2];"
               :: "r"(dst), "l"(tm), "r"(bar), "r"(c0), "r"(c1) : "memory");
}
__device__ __forceinline__ void tma_load_2d_mc(uint32_t dst, const CUtensorMap* tm, uint32_t bar, int c0, int c1) {
  asm volatile("cp.async.bulk.tensor.2d.shared::cluster.global.mbarrier::complete_tx::bytes.multicast::cluster [%0], [%1, {%3, %4}], [%2], %5;"
               :: "r"(dst), "l"(tm), "r"(bar), "r"(c0), "r"(c1), "h"((uint16_t)3) : "memory");
}
__device__ __forceinline__ void tma_store_2d(const CUtensorMap* tm, uint32_t src, int c0, int c1) {
  asm volatile("cp.async.bulk.tensor.2d.global.shared::cta.bulk_group [%0, {%2, %3}], [%1];"
               :: "l"(tm), "r"(src), "r"(c0), "r"(c1) : "memory");
}
__device__ __forceinline__ void bulk_commit_wait() {
  asm volatile("cp.async.bulk.commit_group;\ncp.async.bulk.wait_group 0;" ::: "memory");
}
__device__ __forceinline__ void prefetch_l2(const void* p, uint32_t bytes) {
  asm volatile("cp.async.bulk.prefetch.L2.global [%0], %1;" :: "l"(p), "r"(bytes) : "memory");
}
__device__ __forceinline__ void prefetch_tmap(const CUtensorMap* tm) {
  asm volatile("prefetch.tensormap [%0];" :: "l"(tm) : "memory");
}
__device__ __forceinline__ void fence_proxy_async_global() { asm volatile("fence.proxy.async.global;" ::: "memory"); }
__device__ __forceinline__ void fence_proxy_async_smem() { asm volatile("fence.proxy.async.shared::cta;" ::: "memory"); }
__device__ __forceinline__ unsigned ld_relaxed(const unsigned* p) {
  unsigned v;
  asm volatile("ld.relaxed.gpu.global.u32 %0, [%1];" : "=r"(v) : "l"(p) : "memory");
  return v;
}
__device__ __forceinline__ void fence_acquire() { asm volatile("fence.acquire.gpu;" ::: "memory"); }
__device__ __forceinline__ void wait_flag(const unsigned* p, unsigned target) {
  int it = 0;
  while ((int)(ld_relaxed(p) - target) < 0 && ++it < (1 << 20)) {}
  fence_acquire();
}
__device__ __forceinline__ void wait_flag_fast(const unsigned* p, unsigned target) {
  unsigned v0 = ld_relaxed(p);
  __nanosleep(100);
  unsigned v1 = ld_relaxed(p);
  __nanosleep(100);
  unsigned v2 = ld_relaxed(p);
  for (int it = 0; it < (1 << 19); it++) {
    if ((int)(v0 - target) >= 0) break;
    v0 = ld_relaxed(p);
    if ((int)(v1 - target) >= 0) break;
    v1 = ld_relaxed(p);
    if ((int)(v2 - target) >= 0) break;
    v2 = ld_relaxed(p);
  }
  fence_acquire();
}
__device__ __forceinline__ void signal_release(unsigned* p) {
  asm volatile("red.release.gpu.global.add.u32 [%0], 1;" :: "l"(p) : "memory");
}
__device__ __forceinline__ void signal_relaxed(unsigned* p) {
  asm volatile("red.relaxed.gpu.global.add.u32 [%0], 1;" :: "l"(p) : "memory");
}
#define SIGNAL_TILE signal_release
template <int ID, int N> __device__ __forceinline__ void bar_arrive() { asm volatile("bar.arrive %0, %1;" :: "n"(ID), "n"(N) : "memory"); }
template <int ID, int N> __device__ __forceinline__ void bar_sync() { asm volatile("bar.sync %0, %1;" :: "n"(ID), "n"(N) : "memory"); }
__device__ __forceinline__ void bar_wg(int wg) { asm volatile("bar.sync %0, 128;" :: "r"(2 + wg) : "memory"); }
__device__ __forceinline__ void cluster_sync() {
  asm volatile("barrier.cluster.arrive.relaxed.aligned;\nbarrier.cluster.wait.aligned;" ::: "memory");
}
__device__ __forceinline__ void cluster_wait() { asm volatile("barrier.cluster.wait.acquire.aligned;" ::: "memory"); }
enum { BAR_CONS = 1, BAR_KV = 4  , BAR_HRECV = 6, BAR_O = 7, BAR_O1 = 8, BAR_X = 9, BAR_X1 = 10, BAR_MID = 11, BAR_WF = 12, BAR_SKEW = 13 };

__device__ __forceinline__ void wgmma_fence() { asm volatile("wgmma.fence.sync.aligned;" ::: "memory"); }
__device__ __forceinline__ void wgmma_commit() { asm volatile("wgmma.commit_group.sync.aligned;" ::: "memory"); }
template <int N> __device__ __forceinline__ void wgmma_wait() { asm volatile("wgmma.wait_group.sync.aligned %0;" :: "n"(N) : "memory"); }

#define ACC64_OUT(d) \
  "+f"(d[0]), "+f"(d[1]), "+f"(d[2]), "+f"(d[3]), "+f"(d[4]), "+f"(d[5]), "+f"(d[6]), "+f"(d[7]), \
  "+f"(d[8]), "+f"(d[9]), "+f"(d[10]), "+f"(d[11]), "+f"(d[12]), "+f"(d[13]), "+f"(d[14]), "+f"(d[15]), \
  "+f"(d[16]), "+f"(d[17]), "+f"(d[18]), "+f"(d[19]), "+f"(d[20]), "+f"(d[21]), "+f"(d[22]), "+f"(d[23]), \
  "+f"(d[24]), "+f"(d[25]), "+f"(d[26]), "+f"(d[27]), "+f"(d[28]), "+f"(d[29]), "+f"(d[30]), "+f"(d[31]), \
  "+f"(d[32]), "+f"(d[33]), "+f"(d[34]), "+f"(d[35]), "+f"(d[36]), "+f"(d[37]), "+f"(d[38]), "+f"(d[39]), \
  "+f"(d[40]), "+f"(d[41]), "+f"(d[42]), "+f"(d[43]), "+f"(d[44]), "+f"(d[45]), "+f"(d[46]), "+f"(d[47]), \
  "+f"(d[48]), "+f"(d[49]), "+f"(d[50]), "+f"(d[51]), "+f"(d[52]), "+f"(d[53]), "+f"(d[54]), "+f"(d[55]), \
  "+f"(d[56]), "+f"(d[57]), "+f"(d[58]), "+f"(d[59]), "+f"(d[60]), "+f"(d[61]), "+f"(d[62]), "+f"(d[63])
#define ACC64_REGS \
  "{%0,%1,%2,%3,%4,%5,%6,%7,%8,%9,%10,%11,%12,%13,%14,%15,%16,%17,%18,%19,%20,%21,%22,%23,%24,%25,%26,%27,%28,%29,%30,%31," \
  "%32,%33,%34,%35,%36,%37,%38,%39,%40,%41,%42,%43,%44,%45,%46,%47,%48,%49,%50,%51,%52,%53,%54,%55,%56,%57,%58,%59,%60,%61,%62,%63}"

template <int scale_d> __device__ __forceinline__ void wgmma_n128(float (&d)[64], uint64_t descA, uint64_t descB) {
  asm volatile("{\n.reg .pred p;\nsetp.ne.b32 p, %66, 0;\n"
               "wgmma.mma_async.sync.aligned.m64n128k16.f32.bf16.bf16 " ACC64_REGS ", %64, %65, p, 1, 1, 0, 1;\n}\n"
               : ACC64_OUT(d) : "l"(descA), "l"(descB), "n"(scale_d));
}
template <int scale_d> __device__ __forceinline__ void wgmma_n256(float (&d)[128], uint64_t descA, uint64_t descB) {
  asm volatile("{\n.reg .pred p;\nsetp.ne.b32 p, %130, 0;\n"
               "wgmma.mma_async.sync.aligned.m64n256k16.f32.bf16.bf16 {%0,%1,%2,%3,%4,%5,%6,%7,%8,%9,%10,%11,%12,%13,%14,%15,%16,%17,%18,%19,%20,%21,%22,%23,%24,%25,%26,%27,%28,%29,%30,%31,%32,%33,%34,%35,%36,%37,%38,%39,%40,%41,%42,%43,%44,%45,%46,%47,%48,%49,%50,%51,%52,%53,%54,%55,%56,%57,%58,%59,%60,%61,%62,%63,%64,%65,%66,%67,%68,%69,%70,%71,%72,%73,%74,%75,%76,%77,%78,%79,%80,%81,%82,%83,%84,%85,%86,%87,%88,%89,%90,%91,%92,%93,%94,%95,%96,%97,%98,%99,%100,%101,%102,%103,%104,%105,%106,%107,%108,%109,%110,%111,%112,%113,%114,%115,%116,%117,%118,%119,%120,%121,%122,%123,%124,%125,%126,%127}, %128, %129, p, 1, 1, 0, 1;\n}\n"
               : "+f"(d[0]), "+f"(d[1]), "+f"(d[2]), "+f"(d[3]), "+f"(d[4]), "+f"(d[5]), "+f"(d[6]), "+f"(d[7]), "+f"(d[8]), "+f"(d[9]), "+f"(d[10]), "+f"(d[11]), "+f"(d[12]), "+f"(d[13]), "+f"(d[14]), "+f"(d[15]), "+f"(d[16]), "+f"(d[17]), "+f"(d[18]), "+f"(d[19]), "+f"(d[20]), "+f"(d[21]), "+f"(d[22]), "+f"(d[23]), "+f"(d[24]), "+f"(d[25]), "+f"(d[26]), "+f"(d[27]), "+f"(d[28]), "+f"(d[29]), "+f"(d[30]), "+f"(d[31]), "+f"(d[32]), "+f"(d[33]), "+f"(d[34]), "+f"(d[35]), "+f"(d[36]), "+f"(d[37]), "+f"(d[38]), "+f"(d[39]), "+f"(d[40]), "+f"(d[41]), "+f"(d[42]), "+f"(d[43]), "+f"(d[44]), "+f"(d[45]), "+f"(d[46]), "+f"(d[47]), "+f"(d[48]), "+f"(d[49]), "+f"(d[50]), "+f"(d[51]), "+f"(d[52]), "+f"(d[53]), "+f"(d[54]), "+f"(d[55]), "+f"(d[56]), "+f"(d[57]), "+f"(d[58]), "+f"(d[59]), "+f"(d[60]), "+f"(d[61]), "+f"(d[62]), "+f"(d[63]), "+f"(d[64]), "+f"(d[65]), "+f"(d[66]), "+f"(d[67]), "+f"(d[68]), "+f"(d[69]), "+f"(d[70]), "+f"(d[71]), "+f"(d[72]), "+f"(d[73]), "+f"(d[74]), "+f"(d[75]), "+f"(d[76]), "+f"(d[77]), "+f"(d[78]), "+f"(d[79]), "+f"(d[80]), "+f"(d[81]), "+f"(d[82]), "+f"(d[83]), "+f"(d[84]), "+f"(d[85]), "+f"(d[86]), "+f"(d[87]), "+f"(d[88]), "+f"(d[89]), "+f"(d[90]), "+f"(d[91]), "+f"(d[92]), "+f"(d[93]), "+f"(d[94]), "+f"(d[95]), "+f"(d[96]), "+f"(d[97]), "+f"(d[98]), "+f"(d[99]), "+f"(d[100]), "+f"(d[101]), "+f"(d[102]), "+f"(d[103]), "+f"(d[104]), "+f"(d[105]), "+f"(d[106]), "+f"(d[107]), "+f"(d[108]), "+f"(d[109]), "+f"(d[110]), "+f"(d[111]), "+f"(d[112]), "+f"(d[113]), "+f"(d[114]), "+f"(d[115]), "+f"(d[116]), "+f"(d[117]), "+f"(d[118]), "+f"(d[119]), "+f"(d[120]), "+f"(d[121]), "+f"(d[122]), "+f"(d[123]), "+f"(d[124]), "+f"(d[125]), "+f"(d[126]), "+f"(d[127])
               : "l"(descA), "l"(descB), "n"(scale_d));
}
template <int scale_d, int tnsp_a> __device__ __forceinline__ void wgmma_n40(float (&d)[20], uint64_t descA, uint64_t descB) {
  asm volatile("{\n.reg .pred p;\nsetp.ne.b32 p, %22, 0;\n"
               "wgmma.mma_async.sync.aligned.m64n40k16.f32.bf16.bf16 {%0,%1,%2,%3,%4,%5,%6,%7,%8,%9,%10,%11,%12,%13,%14,%15,%16,%17,%18,%19}, %20, %21, p, 1, 1, %23, 1;\n}\n"
               : "+f"(d[0]), "+f"(d[1]), "+f"(d[2]), "+f"(d[3]), "+f"(d[4]), "+f"(d[5]), "+f"(d[6]), "+f"(d[7]),
                 "+f"(d[8]), "+f"(d[9]), "+f"(d[10]), "+f"(d[11]), "+f"(d[12]), "+f"(d[13]), "+f"(d[14]), "+f"(d[15]),
                 "+f"(d[16]), "+f"(d[17]), "+f"(d[18]), "+f"(d[19])
               : "l"(descA), "l"(descB), "n"(scale_d), "n"(tnsp_a));
}
__device__ __forceinline__ uint64_t make_desc(uint32_t addr, uint32_t lbo_bytes, uint32_t sbo_bytes) {
  return (uint64_t)((addr & 0x3FFFF) >> 4) | ((uint64_t)(lbo_bytes >> 4) << 16) | ((uint64_t)(sbo_bytes >> 4) << 32) | (1ull << 62);
}

__device__ __forceinline__ void ldsm_x4(uint32_t addr, uint32_t& r0, uint32_t& r1, uint32_t& r2, uint32_t& r3) {
  asm volatile("ldmatrix.sync.aligned.m8n8.x4.shared.b16 {%0,%1,%2,%3}, [%4];" : "=r"(r0), "=r"(r1), "=r"(r2), "=r"(r3) : "r"(addr) : "memory");
}
__device__ __forceinline__ void ldsm_x4_t(uint32_t addr, uint32_t& r0, uint32_t& r1, uint32_t& r2, uint32_t& r3) {
  asm volatile("ldmatrix.sync.aligned.m8n8.x4.trans.shared.b16 {%0,%1,%2,%3}, [%4];" : "=r"(r0), "=r"(r1), "=r"(r2), "=r"(r3) : "r"(addr) : "memory");
}
__device__ __forceinline__ void stsm_x4(uint32_t addr, uint32_t r0, uint32_t r1, uint32_t r2, uint32_t r3) {
  asm volatile("stmatrix.sync.aligned.m8n8.x4.shared.b16 [%0], {%1,%2,%3,%4};" :: "r"(addr), "r"(r0), "r"(r1), "r"(r2), "r"(r3) : "memory");
}
__device__ __forceinline__ uint4 lds128(uint32_t addr) {
  uint4 v;
  asm volatile("ld.shared.v4.u32 {%0,%1,%2,%3}, [%4];" : "=r"(v.x), "=r"(v.y), "=r"(v.z), "=r"(v.w) : "r"(addr) : "memory");
  return v;
}
__device__ __forceinline__ void sts128(uint32_t addr, uint32_t a, uint32_t b, uint32_t c, uint32_t d) {
  asm volatile("st.shared.v4.u32 [%0], {%1,%2,%3,%4};" :: "r"(addr), "r"(a), "r"(b), "r"(c), "r"(d) : "memory");
}
__device__ __forceinline__ float2 lds64f(uint32_t addr) {
  float2 v;
  asm volatile("ld.shared.v2.f32 {%0,%1}, [%2];" : "=f"(v.x), "=f"(v.y) : "r"(addr) : "memory");
  return v;
}
__device__ __forceinline__ void sts64f(uint32_t addr, float a, float b) {
  asm volatile("st.shared.v2.f32 [%0], {%1,%2};" :: "r"(addr), "f"(a), "f"(b) : "memory");
}
__device__ __forceinline__ float4 lds128f(uint32_t addr) {
  float4 v;
  asm volatile("ld.shared.v4.f32 {%0,%1,%2,%3}, [%4];" : "=f"(v.x), "=f"(v.y), "=f"(v.z), "=f"(v.w) : "r"(addr) : "memory");
  return v;
}
__device__ __forceinline__ void mma_bf16(float (&c)[4], uint32_t a0, uint32_t a1, uint32_t a2, uint32_t a3, uint32_t b0, uint32_t b1) {
  asm("mma.sync.aligned.m16n8k16.row.col.f32.bf16.bf16.f32 {%0,%1,%2,%3}, {%4,%5,%6,%7}, {%8,%9}, {%0,%1,%2,%3};"
               : "+f"(c[0]), "+f"(c[1]), "+f"(c[2]), "+f"(c[3]) : "r"(a0), "r"(a1), "r"(a2), "r"(a3), "r"(b0), "r"(b1));
}
__device__ __forceinline__ uint32_t movm_t(uint32_t v) {
  uint32_t r;
  asm volatile("movmatrix.sync.aligned.m8n8.trans.b16 %0, %1;" : "=r"(r) : "r"(v));
  return r;
}
__device__ __forceinline__ uint32_t pack_bf16(float lo, float hi) {
  uint32_t r;
  asm("cvt.rn.bf16x2.f32 %0, %1, %2;" : "=r"(r) : "f"(hi), "f"(lo));
  return r;
}
__device__ __forceinline__ float bf_lo(uint32_t v) { return __uint_as_float(v << 16); }
__device__ __forceinline__ float bf_hi(uint32_t v) { return __uint_as_float(v & 0xFFFF0000u); }
__device__ __forceinline__ float ex2(float x) { float r; asm("ex2.approx.ftz.f32 %0, %1;" : "=f"(r) : "f"(x)); return r; }
__device__ __forceinline__ float rcp_fast(float x) { float r; asm("rcp.approx.ftz.f32 %0, %1;" : "=f"(r) : "f"(x)); return r; }
__device__ __forceinline__ void red_v4(float* p, float a, float b, float c, float d) {
  asm volatile("red.global.add.v4.f32 [%0], {%1, %2, %3, %4};" :: "l"(p), "f"(a), "f"(b), "f"(c), "f"(d) : "memory");
}
__device__ __forceinline__ void red_v2(float* p, float a, float b) {
  asm volatile("red.global.add.v2.f32 [%0], {%1, %2};" :: "l"(p), "f"(a), "f"(b) : "memory");
}
__device__ __forceinline__ void red_f32(float* p, float a) {
  asm volatile("red.global.add.f32 [%0], %1;" :: "l"(p), "f"(a) : "memory");
}

__device__ __forceinline__ void st_ll(uint4* p, uint32_t d0, uint32_t d1, uint32_t tag) {
  asm volatile("{\n.reg .b64 a, b;\nmov.b64 a, {%1, %3};\nmov.b64 b, {%2, %3};\nst.relaxed.gpu.global.v2.b64 [%0], {a, b};\n}\n"
               :: "l"(p), "r"(d0), "r"(d1), "r"(tag) : "memory");
}
__device__ __forceinline__ uint4 ld_ll(const uint4* p) {
  uint4 v;
  asm volatile("{\n.reg .b64 a, b;\nld.relaxed.gpu.global.v2.b64 {a, b}, [%4];\nmov.b64 {%0, %1}, a;\nmov.b64 {%2, %3}, b;\n}\n"
               : "=r"(v.x), "=r"(v.y), "=r"(v.z), "=r"(v.w) : "l"(p) : "memory");
  return v;
}
__device__ __forceinline__ void st_b128(uint4* p, uint32_t a, uint32_t b, uint32_t c, uint32_t d) {
  asm volatile("{\n.reg .b128 v;\nmov.b128 v, {%1, %2, %3, %4};\nst.relaxed.gpu.global.b128 [%0], v;\n}\n" :: "l"(p), "r"(a), "r"(b), "r"(c), "r"(d) : "memory");
}
__device__ __forceinline__ uint4 ld_b128(const uint4* p) {
  uint4 v;
  asm volatile("{\n.reg .b128 v;\nld.relaxed.gpu.global.b128 v, [%4];\nmov.b128 {%0, %1, %2, %3}, v;\n}\n" : "=r"(v.x), "=r"(v.y), "=r"(v.z), "=r"(v.w) : "l"(p) : "memory");
  return v;
}
__device__ __forceinline__ void bulk_reduce_f32(float* dst, uint32_t src, uint32_t bytes) {
  asm volatile("cp.reduce.async.bulk.global.shared::cta.bulk_group.add.f32 [%0], [%1], %2;" :: "l"(dst), "r"(src), "r"(bytes) : "memory");
}

constexpr float LOG2E = 1.4426950408889634f;

struct Params {
  const __nv_bfloat16* x0;
  const __nv_bfloat16* wA_qkv;
  const __nv_bfloat16* wA_o;
  const __nv_bfloat16* wB_qkv;
  const __nv_bfloat16* wB_phi;
  const __nv_bfloat16* wB_o;
  __nv_bfloat16* out;
};

#define ACC_DEF(d, n) _Pragma("unroll") for (int i_ = 0; i_ < (n); i_++) asm volatile("" : "=f"(d[i_]))
#define ACC_FENCE(d, n) _Pragma("unroll") for (int i_ = 0; i_ < (n); i_++) asm volatile("" : "+f"(d[i_]) :: "memory")

#define STAGE_ACC_LN(acc, off, p0, csa, NB, SENDP) \
  _Pragma("unroll") for (int b_ = 0; b_ < 8; b_ += (NB)) { \
    float4 c_[NB]; \
    uint32_t w_[NB][4]; \
    _Pragma("unroll") for (int j_ = 0; j_ < (NB); j_++) c_[j_] = lds128f((csa) + (b_ + j_) * 64); \
    _Pragma("unroll") for (int j_ = 0; j_ < (NB); j_++) { \
      const int o_ = (off) + (b_ + j_) * 8; \
      w_[j_][0] = pack_bf16(rs0 * fmaf(nm0, c_[j_].x, acc[o_ + 0]), rs0 * fmaf(nm0, c_[j_].y, acc[o_ + 1])); \
      w_[j_][1] = pack_bf16(rs1 * fmaf(nm1, c_[j_].x, acc[o_ + 2]), rs1 * fmaf(nm1, c_[j_].y, acc[o_ + 3])); \
      w_[j_][2] = pack_bf16(rs0 * fmaf(nm0, c_[j_].z, acc[o_ + 4]), rs0 * fmaf(nm0, c_[j_].w, acc[o_ + 5])); \
      w_[j_][3] = pack_bf16(rs1 * fmaf(nm1, c_[j_].z, acc[o_ + 6]), rs1 * fmaf(nm1, c_[j_].w, acc[o_ + 7])); \
    } \
    if ((SENDP) >= 0 && hsend) { \
      _Pragma("unroll") for (int j_ = 0; j_ < (NB); j_++) { \
        w_[j_][0] = (w_[j_][0] & ~1u) | hbit; \
        st_b128(hdst + ((SENDP) * 8 + b_ + j_) * 32, w_[j_][0], w_[j_][1], w_[j_][2], w_[j_][3]); \
      } \
    } \
    if ((SENDP) == 0) mbar_wait(bar_done + 15 * 8, 0); \
    _Pragma("unroll") for (int j_ = 0; j_ < (NB); j_++) \
      stsm_x4((SENDP) == 1 ? (p0) + ((b_ + j_) >> 1) * 8192 + (srowoff >> 1) + ((((uint32_t)((b_ + j_) & 1) << 5) + lhi) ^ lsw2) \
                           : (p0) + ((b_ + j_) >> 2) * SLOT + srowoff + ((((uint32_t)((b_ + j_) & 3) << 5) + lhi) ^ lsw), \
              w_[j_][0], w_[j_][1], w_[j_][2], w_[j_][3]); \
  }
#define PHI_LOAD(acc, csa) \
  _Pragma("unroll") for (int j_ = 0; j_ < 8; j_++) { \
    const float4 c_ = lds128f((csa) + j_ * 64); \
    p0[j_ * 4 + 0] = fmaf(nm0, c_.x, acc[j_ * 8 + 0]); p0[j_ * 4 + 1] = fmaf(nm0, c_.y, acc[j_ * 8 + 1]); \
    p0[j_ * 4 + 2] = fmaf(nm0, c_.z, acc[j_ * 8 + 4]); p0[j_ * 4 + 3] = fmaf(nm0, c_.w, acc[j_ * 8 + 5]); \
    p1[j_ * 4 + 0] = fmaf(nm1, c_.x, acc[j_ * 8 + 2]); p1[j_ * 4 + 1] = fmaf(nm1, c_.y, acc[j_ * 8 + 3]); \
    p1[j_ * 4 + 2] = fmaf(nm1, c_.z, acc[j_ * 8 + 6]); p1[j_ * 4 + 3] = fmaf(nm1, c_.w, acc[j_ * 8 + 7]); \
  }
__device__ __forceinline__ float rmax32(const float (&p)[32]) {
  float m[4];
#pragma unroll
  for (int j = 0; j < 4; j++) m[j] = fmaxf(p[j], p[j + 4]);
#pragma unroll
  for (int j = 8; j < 32; j++) m[j & 3] = fmaxf(m[j & 3], p[j]);
  return fmaxf(fmaxf(m[0], m[1]), fmaxf(m[2], m[3]));
}
__device__ __forceinline__ float rmin32(const float (&p)[32]) {
  float m[4];
#pragma unroll
  for (int j = 0; j < 4; j++) m[j] = fminf(p[j], p[j + 4]);
#pragma unroll
  for (int j = 8; j < 32; j++) m[j & 3] = fminf(m[j & 3], p[j]);
  return fminf(fminf(m[0], m[1]), fminf(m[2], m[3]));
}
__device__ __forceinline__ float exps32(float (&o)[32], const float (&p)[32], float c, float b) {
  float s[4] = {0.f, 0.f, 0.f, 0.f};
#pragma unroll
  for (int j = 0; j < 32; j++) { o[j] = ex2(fmaf(p[j], c, b)); s[j & 3] += o[j]; }
  return rcp_fast((s[0] + s[1]) + (s[2] + s[3]));
}
__device__ __forceinline__ void store32(const float (&e)[32], float inv, uint32_t dst, uint32_t dsw, int c0) {
#pragma unroll
  for (int j = 0; j < 4; j++)
    sts128(dst + (((c0 + j) << 4) ^ dsw), pack_bf16(e[j * 8] * inv, e[j * 8 + 1] * inv), pack_bf16(e[j * 8 + 2] * inv, e[j * 8 + 3] * inv),
           pack_bf16(e[j * 8 + 4] * inv, e[j * 8 + 5] * inv), pack_bf16(e[j * 8 + 6] * inv, e[j * 8 + 7] * inv));
}
#define SCHED_FENCE() asm volatile("pmevent 0;" ::: "memory")
#define PIN32(a) _Pragma("unroll") for (int i_ = 0; i_ < 32; i_++) asm volatile("" : "+f"((a)[i_]))

__global__ void __cluster_dims__(2, 1, 1) __launch_bounds__(384, 1)
mega_kernel(const __grid_constant__ CUtensorMap tm_x0, const __grid_constant__ CUtensorMap tm_xo,
            const __grid_constant__ CUtensorMap tm_o, const __grid_constant__ CUtensorMap tm_wf,
            const __grid_constant__ CUtensorMap tm_wqA, const __grid_constant__ CUtensorMap tm_wqB,
            const __grid_constant__ CUtensorMap tm_woA, const __grid_constant__ CUtensorMap tm_woB,
            const __grid_constant__ CUtensorMap tm_phi, const Params prm) {
  extern __shared__ __align__(1024) uint8_t smem_raw[];
  const uint32_t sbase = smem_u32(smem_raw);
  const uint32_t bar_full = sbase + OFF_BAR;
  const uint32_t bar_done = bar_full + 128;
  const uint32_t bar_stat = bar_full + 256, bar_epi = bar_full + 264, bar_x0 = bar_full + 272, bar_wf = bar_full + 280;

  const int warp = __shfl_sync(0xffffffffu, threadIdx.x >> 5, 0), lane = threadIdx.x & 31;
  uint32_t rank;
  asm volatile("mov.u32 %0, %%cluster_ctarank;" : "=r"(rank));
  const int cta = (int)blockIdx.x - NAUX;
  const int cl = cta >> 1;
  const int jj = cl & 7, cc = cl >> 3;
  const int mm = cc * 2 + (int)rank;

  unsigned epoch;
  asm volatile("ld.relaxed.gpu.global.u32 %0, [%1];" : "=r"(epoch) : "l"(&g_flags.epoch.v) : "memory");
  const unsigned ep1 = epoch + 1;

  if (cta >= 0) {
    {
      const int tx = threadIdx.x;
      const __nv_bfloat16* pf = (tx < 128) ? prm.x0 + (size_t)(mm * 128 + tx) * D_MODEL + jj * 128
                                           : prm.wA_qkv + (size_t)(jj * 128 + (tx & 63)) * 3072 + ((tx - 128) >> 6) * 1024 + jj * 128 + rank * 64;
      if (tx < 320) asm volatile("prefetch.global.L2 [%0];" :: "l"(pf));
      else if (tx == 320) prefetch_tmap(&tm_x0);
      else if (tx == 352) prefetch_tmap(&tm_wqA);
    }
    if (threadIdx.x == 0) {
      PROFT(79);
      for (int i = 0; i < 16; i++) { mbar_init(bar_full + i * 8, 1); mbar_init(bar_done + i * 8, 16); }
      mbar_init(bar_stat, 2); mbar_init(bar_epi, 16); mbar_init(bar_x0, 1); mbar_init(bar_wf, 2);
      asm volatile("fence.mbarrier_init.release.cluster;" ::: "memory");
    }
    __syncthreads();
    asm volatile("barrier.cluster.arrive.relaxed.aligned;" ::: "memory");
  }

  if (cta < 0) {
    const int w = blockIdx.x * 12 + warp;
    const uint32_t buf = sbase + warp * SLOT, bar = sbase + OFF_BAR + warp * 16;
    const uint32_t lsw = (lane & 7) << 4, lhi = (lane >> 4) << 4, lrow = (lane & 15) * 128;
    const bool el = elect_one();
    if (el) {
      mbar_init(bar, 1); mbar_init(bar + 8, 1);
      asm volatile("fence.mbarrier_init.release.cluster;" ::: "memory");
    }
#pragma unroll 1
    for (int ph = 0; ph < (NLAYERS > 1 ? 2 : 1); ph++) {
      const CUtensorMap* tm = ph ? (w < 32 ? &tm_wf : &tm_wqB) : &tm_wqA;
      if (el) {
        if (ph && w < 32) { wait_flag(&g_flags.wfready[(w & 15) >> 1].v, ep1 * 16); fence_proxy_async_global(); }
        for (int i = 0; i < 2; i++) { mbar_expect_tx(bar + i * 8, 8192); tma_load_2d(buf + i * 8192, tm, bar + i * 8, w * 64, kslice((w & 15) >> 1, i) * 64); }
      }
      __syncwarp();
      float cs[8][4];
#pragma unroll
      for (int i = 0; i < 8; i++) cs[i][0] = cs[i][1] = cs[i][2] = cs[i][3] = 0.f;
#pragma unroll 1
      for (int n = 0; n < 16; n++) {
        const uint32_t tb = buf + (n & 1) * 8192 + lrow;
        mbar_wait(bar + (n & 1) * 8, (n >> 1) & 1);
#pragma unroll
        for (int i = 0; i < 16; i++) {
          uint32_t b0, b1, b2, b3;
          ldsm_x4_t(tb + (i >> 2) * 2048 + (((i & 3) * 32 + lhi) ^ lsw), b0, b1, b2, b3);
          mma_bf16(cs[2 * (i & 3)], 0x3F803F80u, 0x3F803F80u, 0x3F803F80u, 0x3F803F80u, b0, b1);
          mma_bf16(cs[2 * (i & 3) + 1], 0x3F803F80u, 0x3F803F80u, 0x3F803F80u, 0x3F803F80u, b2, b3);
        }
        __syncwarp();
        if (el && n < 14) { mbar_expect_tx(bar + (n & 1) * 8, 8192); tma_load_2d(buf + (n & 1) * 8192, tm, bar + (n & 1) * 8, w * 64, kslice((w & 15) >> 1, n + 2) * 64); }
      }
      if (lane < 4) {
#pragma unroll
        for (int i = 0; i < 8; i++) st_ll(g_colsum[ph] + w * 32 + i * 4 + lane, __float_as_uint(cs[i][0]), __float_as_uint(cs[i][1]), ep1);
      }
      __syncwarp();
      if (el) {
      }
    }
  } else if (warp >= 8) {
    asm volatile("setmaxnreg.dec.sync.aligned.u32 40;");
    if (warp == 8) {
      const bool el = elect_one();
      cluster_wait();
      if (el) {
        const int col = jj * 128 + (int)rank * 64;
#pragma unroll 1
        for (int l = 0; l < NLAYERS; l++) {
          const CUtensorMap* tqk = (l & 1) ? &tm_wf : &tm_wqA;
          const CUtensorMap* tv = (l & 1) ? &tm_wqB : &tm_wqA;
          const CUtensorMap* two = (l & 1) ? &tm_woB : &tm_woA;
          if (l == 1) { wait_flag(&g_flags.wfready[jj].v, ep1 * 16); fence_proxy_async_global(); }
          uint32_t dst = sbase + rank * 8192;
#pragma unroll 1
          for (int i = 0; i < 16; i++) {
            if (i >= 3) mbar_wait_sl(bar_done + (i - 3) * 8, 0);
            else if (l) mbar_wait_sl(bar_done + (11 + 2 * i) * 8, 1);
            else if (i == 1) __nanosleep(STAG1);
            else if (i == 2) mbar_wait_sl(bar_full, 0);
            const uint32_t fb = bar_full + i * 8;
            mbar_expect_tx(fb, (i < 2 && l) ? 3 * SLOT : 4 * SLOT);
            const int kk = kslice(jj, i);
            tma_load_2d_mc(dst, tqk, fb, col, kk * 64);
            tma_load_2d_mc(dst + SLOT, tqk, fb, col + 1024, kk * 64);
            tma_load_2d_mc(dst + 2 * SLOT, tv, fb, col + 2048, kk * 64);
            if (l == 0 && i < 3) PROFT(217 + i);
            dst += 3 * SLOT;
            if (dst >= sbase + 9 * SLOT) dst -= 9 * SLOT;
          }
#pragma unroll 1
          for (int n = 0; n < 16; n++) {
            const int s = (n < 2) ? 1 - n : n;
            if (n >= 6) mbar_wait_sl(bar_done + (n - 6) * 8, 1);
            else if (n < 2) mbar_wait_sl(bar_done + (13 + n) * 8, 0);
            else if (n == 3) {
              mbar_wait_sl(bar_epi, l & 1);
              if (l == 0 && NLAYERS > 1) mbar_wait_sl(bar_wf, 0);
            }
            const uint32_t fb = bar_full + s * 8;
            mbar_expect_tx(fb, (s < 2) ? SLOT : 2 * SLOT);
            tma_load_2d_mc(sbase + rank * 8192 + (uint32_t)((WO_BSLOT >> (4 * s)) & 15) * SLOT, two, fb, col, kslice(jj, s) * 64);
          }
        }
      }
      __syncwarp();
    } else if (warp == 9) {
      const bool el = elect_one();
      if (el) {
        tma_load_2d(sbase + OFF_X, &tm_x0, bar_full, jj * 128, mm * 128);
        PROFT(216);
        __nanosleep(STAG1);
        tma_load_2d(sbase + OFF_X + SLOT, &tm_x0, bar_full + 8, jj * 128 + 64, mm * 128);
        mbar_wait_sl(bar_full, 0);
      }
#pragma unroll 1
      for (int l = 0; l < NLAYERS; l++) {
        if (el) {
          const CUtensorMap* tx = l ? &tm_xo : &tm_x0;
          if (l) {
            mbar_wait_sl(bar_done + 15 * 8, 1);
            wait_flag_fast(&g_flags.xready[l][mm][0].v, ep1 * 8);
            fence_proxy_async_global();
            PROFT(160 + l * 8);
          }
          uint32_t dst = sbase + 9 * SLOT;
#pragma unroll 1
          for (int i = 2; i < 16; i++) {
            if (i >= 5) mbar_wait_sl(bar_done + (i - 3) * 8, 0);
            if (i == 9 && l) { wait_flag(&g_flags.xready[l][mm][1].v, ep1 * 8); fence_proxy_async_global(); }
            tma_load_2d(dst, tx, bar_full + i * 8, kslice(jj, i) * 64, mm * 128);
            if (l < 2 && i >= 4 && i < 8) prefetch_l2((const char*)(l ? prm.wB_o : prm.wA_o) + (size_t)cta * 16384 + (i - 4) * 4096, 4096);
            if (l == 0 && i >= 8) prefetch_l2((const char*)prm.wB_qkv + (size_t)cta * 49152 + (i - 8) * 6144, 6144);
            dst += SLOT;
            if (dst == sbase + 12 * SLOT) dst = sbase + 9 * SLOT;
          }
        }
        if (el) {
          if (l == 0 && NLAYERS > 1) {
            mbar_wait_sl(bar_done + 15 * 8, 0);
            mbar_expect_tx(bar_x0, 2 * SLOT + 8192);
            tma_load_2d(sbase + 10 * SLOT + 8192, &tm_phi, bar_x0, 0, jj * 128);
#pragma unroll 1
            for (int i = 0; i < 4; i++) tma_load_2d(sbase + (i >> 1) * 3 * SLOT + (i & 1) * 8192, &tm_wqB, bar_x0, (i >> 1) * 1024 + jj * 128 + (i & 1) * 64, mm * 64);
          }
          mbar_wait_sl(bar_epi, l & 1);
          wait_flag_fast(&g_flags.oready[l][mm][0].v, ep1 * 8);
          fence_proxy_async_global();
          PROFT(163 + l * 8);
#pragma unroll 1
          for (int s = 2; s < 16; s++) {
            if (s >= 6) mbar_wait_sl(bar_done + (s - 6) * 8, 1);
            if (s == 7) { wait_flag(&g_flags.oready[l][mm][1].v, ep1 * 8); fence_proxy_async_global(); }
            tma_load_2d(sbase + (uint32_t)((WO_ASLOT >> (4 * s)) & 15) * SLOT, &tm_o, bar_full + s * 8, kslice(jj, s) * 64, mm * 128);
          }
        }
      }
      __syncwarp();
      cluster_wait();
    } else {
      const int hw = warp - 10, ht = hw * 32 + lane;
      const bool el = elect_one();
      cluster_wait();
      mbar_wait_sl(bar_full, 0);
      mbar_wait_sl(bar_full + 8, 0);
      if (hw) {
#pragma unroll 1
        for (int b = 0; b < 2; b++) {
          float4* z = reinterpret_cast<float4*>(g_kv[b] + (jj * 4) * KVH + mm * (4 * KVH / 16)) + lane;
#pragma unroll
          for (int i = 0; i < 5; i++) z[i * 32] = make_float4(0.f, 0.f, 0.f, 0.f);
        }
      }
#pragma unroll 1
      for (int l = 0; l < NLAYERS; l++) {
        const uint32_t tag = ep1 * 4 + l;
        if (l) mbar_wait_sl(bar_done, 0);
#pragma unroll 1
        for (int rr = 0; rr < 2; rr++) {
          const uint32_t a = sbase + OFF_X + (hw * 64 + rr * 32 + lane) * 128, sw = (lane & 7) << 4;
          uint32_t w0;
          asm volatile("ld.shared.u32 %0, [%1];" : "=r"(w0) : "r"(a) : "memory");
          const float pv = bf_lo(w0);
          float s0 = 0.f, s1 = 0.f, q0 = 0.f, q1 = 0.f;
#pragma unroll 1
          for (int c = 0; c < 16; c += 4) {
            uint4 v[4];
#pragma unroll
            for (int i = 0; i < 4; i++) v[i] = lds128(a + (c >> 3) * SLOT + ((((c & 7) + i) << 4) ^ sw));
#pragma unroll
            for (int i = 0; i < 4; i++) {
              float d;
              d = bf_lo(v[i].x) - pv; s0 += d; q0 = fmaf(d, d, q0); d = bf_hi(v[i].x) - pv; s1 += d; q1 = fmaf(d, d, q1);
              d = bf_lo(v[i].y) - pv; s0 += d; q0 = fmaf(d, d, q0); d = bf_hi(v[i].y) - pv; s1 += d; q1 = fmaf(d, d, q1);
              d = bf_lo(v[i].z) - pv; s0 += d; q0 = fmaf(d, d, q0); d = bf_hi(v[i].z) - pv; s1 += d; q1 = fmaf(d, d, q1);
              d = bf_lo(v[i].w) - pv; s0 += d; q0 = fmaf(d, d, q0); d = bf_hi(v[i].w) - pv; s1 += d; q1 = fmaf(d, d, q1);
            }
          }
          s0 += s1; q0 += q1;
          const float mu = s0 * (1.f / 128.f);
          st_ll(g_stats + (size_t)(mm * 128 + hw * 64 + rr * 32 + lane) * 8 + jj, __float_as_uint(pv + mu), __float_as_uint(fmaf(-s0, mu, q0)), tag);
        }
#pragma unroll 1
        for (int rr = 0; rr < 2; rr++) {
          const uint4* srow = g_stats + (size_t)(mm * 128 + hw * 64 + rr * 32 + lane) * 8;
          float sm[8], m2 = 0.f;
#pragma unroll
          for (int hf = 0; hf < 2; hf++) {
            uint32_t bad;
            int it = 0;
            float q;
            do {
              bad = 0; q = 0.f;
#pragma unroll
              for (int i = 0; i < 4; i++) {
                const uint4 v = ld_ll(srow + hf * 4 + i);
                sm[hf * 4 + i] = __uint_as_float(v.x); q += __uint_as_float(v.z);
                bad |= (v.y ^ tag) | (v.w ^ tag);
              }
            } while (bad && ++it < (1 << 18));
            m2 += q;
          }
          const float mean = (((sm[0] + sm[1]) + (sm[2] + sm[3])) + ((sm[4] + sm[5]) + (sm[6] + sm[7]))) * 0.125f;
          float dd = 0.f;
#pragma unroll
          for (int i = 0; i < 8; i++) { const float e = sm[i] - mean; dd = fmaf(e, e, dd); }
          const float rs = rsqrtf(fmaxf(fmaf(dd, 128.f, m2), 0.f) * (1.f / 1024.f) + 1e-5f);
          asm volatile("st.shared.v2.f32 [%0], {%1, %2};" :: "r"(sbase + OFF_ST + (hw * 64 + rr * 32 + lane) * 8), "f"(rs), "f"(-mean) : "memory");
        }
        {
          const uint4* src = g_colsum[l & 1] + jj * 64 + ht;
          const uint32_t dst = sbase + OFF_CS + (ht >> 3) * 64 + (ht & 3) * 16 + ((ht >> 2) & 1) * 8;
          uint32_t bad;
          int it = 0;
          do {
            bad = 0;
#pragma unroll
            for (int p = 0; p < 3; p++) {
              const uint4 v = ld_ll(src + p * 512);
              bad |= (v.y ^ ep1) | (v.w ^ ep1);
              sts64f(dst + p * 512, __uint_as_float(v.x), __uint_as_float(v.z));
            }
            if (bad) __nanosleep(200);
          } while (bad && ++it < (1 << 16));
          __syncwarp();
          if (el) { mbar_arrive_local(bar_stat); PROFT(192 + l * 2 + hw); }
        }
        if ((l & 1) && hw) {
          bar_sync<BAR_KV, 288>();
          if (el) { PROFT(166 + l * 8); signal_release(&g_flags.kvready[l >> 1][jj].v); PROFT(167 + l * 8); }
        }
        __syncwarp();
        if (hw == 0) {
#pragma unroll 1
          for (int e = 0; e < 4; e++) {
            asm volatile("bar.sync %0, 288;" :: "r"(BAR_O + e) : "memory");
            if (el) {
              if (!(e & 1)) PROFT(161 + l * 8 + (e >> 1) * 3);
              tma_store_2d((e & 2) ? &tm_xo : &tm_o, sbase + ((e & 2) ? 10 : 4) * SLOT + e * SLOT, jj * 128 + (e & 1) * 64, mm * 128);
              if (!(e == 2 && l == NLAYERS - 1)) bulk_commit_wait();
              if (!(e & 1)) PROFT(208 + l * 2 + (e >> 1));
              if (e < 2) SIGNAL_TILE(&g_flags.oready[l][mm][e].v);
              else if (l < NLAYERS - 1) SIGNAL_TILE(&g_flags.xready[l + 1][mm][e & 1].v);
              if (!(e & 1)) PROFT(162 + l * 8 + (e >> 1) * 3);
            }
            __syncwarp();
          }
        } else {
          if (l == 0 && NLAYERS > 1) {
            bar_sync<BAR_WF, 288>();
            if (el) {
#pragma unroll 1
              for (int i = 0; i < 4; i++) tma_store_2d(&tm_wf, sbase + (i >> 1) * 3 * SLOT + (i & 1) * 8192, (i >> 1) * 1024 + jj * 128 + (i & 1) * 64, mm * 64);
              asm volatile("cp.async.bulk.commit_group;\ncp.async.bulk.wait_group.read 0;" ::: "memory");
              mbar_arrive_remote(bar_wf, 0); mbar_arrive_remote(bar_wf, 1);
              asm volatile("cp.async.bulk.wait_group 0;" ::: "memory");
              signal_release(&g_flags.wfready[jj].v);
              PROFT(204);
            }
            __syncwarp();
          }
          mbar_wait_sl(bar_done, 1);
        }
      }
    }
    cluster_sync();
  } else {
    asm volatile("setmaxnreg.inc.sync.aligned.u32 232;");
    const int tid = threadIdx.x;
    const int wg = warp >> 2;
    const int g = lane >> 2, t = lane & 3;
    const int r0 = warp * 16;
    const uint32_t srowoff = (r0 + (lane & 15)) * 128;
    const uint32_t lsw = (lane & 7) << 4, lhi = (lane >> 4) << 4, lsw2 = (lane & 6) << 3;
    const uint32_t pK0 = sbase + SLOT, pQ0 = sbase + 4 * SLOT, pV0 = sbase + 7 * SLOT, pX0 = sbase + OFF_X;
    cluster_wait();
    PROF(0);
#define LOAD_X() \
    _Pragma("unroll") for (int j = 0; j < 8; j++) { \
      uint32_t x0, x1, x2, x3; \
      ldsm_x4(pX0 + (j >> 2) * SLOT + srowoff + ((((uint32_t)(j & 3) << 5) + lhi) ^ lsw), x0, x1, x2, x3); \
      acc[j * 8 + 0] = bf_lo(x0); acc[j * 8 + 1] = bf_hi(x0); acc[j * 8 + 2] = bf_lo(x1); acc[j * 8 + 3] = bf_hi(x1); \
      acc[j * 8 + 4] = bf_lo(x2); acc[j * 8 + 5] = bf_hi(x2); acc[j * 8 + 6] = bf_lo(x3); acc[j * 8 + 7] = bf_hi(x3); \
    }

#pragma unroll 1
    for (int l = 0; l < NLAYERS; l++) {
      bar_wg(wg);
      PROF(1 + l * 16);
      float accq[64], acckv[128];
      ACC_DEF(accq, 64); ACC_DEF(acckv, 128);
      {
        uint32_t a = sbase + OFF_X + wg * 8192, bst = sbase;
#define QKV_STEP(SC0) { \
          const uint64_t da = make_desc(a, 16, 1024); \
          a += SLOT; if (a >= sbase + 14 * SLOT) a -= 5 * SLOT; else if (i >= 2 && a >= sbase + 12 * SLOT) a -= 3 * SLOT; \
          const uint64_t db = make_desc(bst, 8192, 1024); \
          bst += 3 * SLOT; if (bst == sbase + 9 * SLOT) bst = sbase; \
          mbar_wait(bar_full + i * 8, 0); \
          if (i == 0) PROF(2 + l * 16); \
          if (i == 2) PROF(3 + l * 16); \
          if (i == 15 && wg == 0) bar_sync<BAR_SKEW, 256>(); \
          wgmma_fence(); \
          wgmma_n128<SC0>(accq, da, db); wgmma_n256<SC0>(acckv, da, db + 1024); \
          _Pragma("unroll") for (int k4 = 1; k4 < 4; k4++) { \
            wgmma_n128<1>(accq, da + k4 * 2, db + k4 * 128); \
            wgmma_n256<1>(acckv, da + k4 * 2, db + 1024 + k4 * 128); \
          } \
          wgmma_commit(); }
        { const int i = 0; QKV_STEP(0) }
#pragma unroll 1
        for (int i = 1; i < 16; i++) {
          QKV_STEP(1)
          if (i == 15 && wg == 1) bar_arrive<BAR_SKEW, 256>();
          wgmma_wait<1>();
          if (lane < 2) mbar_arrive_remote(bar_done + (i - 1) * 8, lane);
        }
      }
      mbar_wait(bar_stat, l & 1);
      const float2 st0_ = lds64f(sbase + OFF_ST + (r0 + g) * 8), st1_ = lds64f(sbase + OFF_ST + (r0 + g + 8) * 8);
      const float rs0 = st0_.x, nm0 = st0_.y, rs1 = st1_.x, nm1 = st1_.y;
      const uint32_t csa = sbase + OFF_CS + t * 16;
      const bool hsend = (warp == 7) && !(l & 1) && (mm < 15);
      uint4* hdst = g_halo + (size_t)(mm * 8 + jj) * 512 + lane;
      const uint32_t hbit = (NLAYERS > 2) ? (l == 0) : (ep1 & 1);
      mbar_wait(bar_done + 14 * 8, 0);
      wgmma_wait<0>();
      ACC_FENCE(accq, 64); ACC_FENCE(acckv, 128);
      if (lane < 2) mbar_arrive_remote(bar_done + 15 * 8, lane);
      PROF(4 + l * 16);
      STAGE_ACC_LN(acckv, 64, pV0, csa + 1024, 4, 1);
      PROF(5 + l * 16);

      if (!(l & 1)) {
        STAGE_ACC_LN(acckv, 0, pK0, csa + 512, 8, 0);
        if (warp == 3) bar_arrive<BAR_MID, 64>();
        STAGE_ACC_LN(accq, 0, pQ0, csa, 8, -1);
        bar_wg(wg);
        if (warp == 4) bar_sync<BAR_MID, 64>();
        PROF(6 + l * 16);
        const uint32_t halo = sbase + 10 * SLOT;
        if (warp == 0) {
          if (mm > 0) {
            int it = 0;
            bool ok;
            do {
              uint4 v[16];
#pragma unroll
              for (int i = 0; i < 16; i++) v[i] = ld_b128(hdst - 8 * 512 + i * 32);
              uint32_t bad = 0;
#pragma unroll
              for (int i = 0; i < 16; i++) {
                bad |= v[i].x ^ hbit;
                stsm_x4(i < 8 ? halo + srowoff + (i >> 2) * 2048 + ((((uint32_t)(i & 3) << 5) + lhi) ^ lsw)
                              : halo + (srowoff >> 1) + (i >> 1) * 1024 + ((((uint32_t)(i & 1) << 5) + lhi) ^ lsw2), v[i].x, v[i].y, v[i].z, v[i].w);
              }
              ok = __all_sync(0xffffffffu, (bad & 1) == 0);
            } while (!ok && ++it < (1 << 16));
          } else {
#pragma unroll 1
            for (int i = 0; i < 16; i++) sts128(halo + i * 512 + lane * 16, 0, 0, 0, 0);
            __syncwarp();
          }
        }
        PROF(7 + l * 16);
        const float sc = 0.17677669529663687f * LOG2E;
        const int e = g & 1;
        uint32_t vmaskA = 0, vmask0 = 0;
#pragma unroll
        for (int jb = 0; jb < 4; jb++) {
          const int c = jb * 8 + 2 * t + e;
          const int d0 = g + 16 - c, d1 = g + 24 - c;
          if (d0 >= 0 && d0 <= 14) { vmaskA |= 1u << jb; if (c >= 16) vmask0 |= 1u << jb; }
          if (d1 >= 0 && d1 <= 14) { vmaskA |= 16u << jb; if (c >= 16) vmask0 |= 16u << jb; }
        }
        const uint32_t vmask = (warp == 0 && mm == 0) ? vmask0 : vmaskA;
#pragma unroll 1
        for (int hp = 0; hp < 2; hp++) {
          const int rb0 = r0;
          const uint32_t qb = pQ0 + hp * SLOT + (rb0 + (lane & 15)) * 128;
          const uint32_t kb1 = pK0 + hp * SLOT + rb0 * 128, vb1 = pV0 + hp * SLOT + rb0 * 64;
          const uint32_t kb0 = rb0 ? kb1 - 2048 : halo + hp * 2048, vb0 = rb0 ? vb1 - 1024 : halo + 4096 + hp * 2048;
          const uint32_t vhs = rb0 ? 8192 : 1024;
          uint32_t qa[2][2][4];
#pragma unroll
          for (int hh = 0; hh < 2; hh++)
#pragma unroll
            for (int ks = 0; ks < 2; ks++) ldsm_x4(qb + ((hh * 64 + ks * 32 + lhi) ^ lsw), qa[hh][ks][0], qa[hh][ks][1], qa[hh][ks][2], qa[hh][ks][3]);
          float s[2][4][4];
#pragma unroll
          for (int jb = 0; jb < 4; jb++) {
            const uint32_t ka = ((jb < 2) ? kb0 : kb1) + ((jb & 1) * 8 + (lane & 7)) * 128;
#pragma unroll
            for (int hh = 0; hh < 2; hh++) {
              uint32_t b0, b1, b2, b3;
              ldsm_x4(ka + ((hh * 64 + ((lane >> 3) << 4)) ^ lsw), b0, b1, b2, b3);
              s[hh][jb][0] = s[hh][jb][1] = s[hh][jb][2] = s[hh][jb][3] = 0.f;
              mma_bf16(s[hh][jb], qa[hh][0][0], qa[hh][0][1], qa[hh][0][2], qa[hh][0][3], b0, b1);
              mma_bf16(s[hh][jb], qa[hh][1][0], qa[hh][1][1], qa[hh][1][2], qa[hh][1][3], b2, b3);
            }
          }
          float v[2][2][4], mx[2][2], sum[2][2];
#pragma unroll
          for (int hh = 0; hh < 2; hh++) {
            mx[hh][0] = mx[hh][1] = -INFINITY;
#pragma unroll
            for (int jb = 0; jb < 4; jb++) {
              const float a0 = e ? s[hh][jb][1] : s[hh][jb][0];
              const float a1 = e ? s[hh][jb][3] : s[hh][jb][2];
              v[hh][0][jb] = (vmask >> jb) & 1 ? a0 : -INFINITY;
              v[hh][1][jb] = (vmask >> (4 + jb)) & 1 ? a1 : -INFINITY;
              mx[hh][0] = fmaxf(mx[hh][0], v[hh][0][jb]); mx[hh][1] = fmaxf(mx[hh][1], v[hh][1][jb]);
            }
          }
#pragma unroll
          for (int o = 1; o <= 2; o <<= 1)
#pragma unroll
            for (int hh = 0; hh < 2; hh++)
#pragma unroll
              for (int r = 0; r < 2; r++) mx[hh][r] = fmaxf(mx[hh][r], __shfl_xor_sync(0xffffffffu, mx[hh][r], o));
#pragma unroll
          for (int hh = 0; hh < 2; hh++)
#pragma unroll
            for (int r = 0; r < 2; r++) {
              const float nb = -mx[hh][r] * sc;
              sum[hh][r] = 0.f;
#pragma unroll
              for (int jb = 0; jb < 4; jb++) { v[hh][r][jb] = ex2(fmaf(v[hh][r][jb], sc, nb)); sum[hh][r] += v[hh][r][jb]; }
            }
#pragma unroll
          for (int o = 1; o <= 2; o <<= 1)
#pragma unroll
            for (int hh = 0; hh < 2; hh++)
#pragma unroll
              for (int r = 0; r < 2; r++) sum[hh][r] += __shfl_xor_sync(0xffffffffu, sum[hh][r], o);
          const uint32_t esh = e * 16;
          float o[2][4][4];
#pragma unroll
          for (int hh = 0; hh < 2; hh++) {
            const float i0 = rcp_fast(sum[hh][0]), i1 = rcp_fast(sum[hh][1]);
#pragma unroll
            for (int dj = 0; dj < 4; dj++) { o[hh][dj][0] = o[hh][dj][1] = o[hh][dj][2] = o[hh][dj][3] = 0.f; }
#pragma unroll
            for (int ks = 0; ks < 2; ks++) {
              const uint32_t pa0 = pack_bf16(v[hh][0][2 * ks] * i0, 0.f) << esh, pa1 = pack_bf16(v[hh][1][2 * ks] * i1, 0.f) << esh;
              const uint32_t pa2 = pack_bf16(v[hh][0][2 * ks + 1] * i0, 0.f) << esh, pa3 = pack_bf16(v[hh][1][2 * ks + 1] * i1, 0.f) << esh;
              const uint32_t va = (ks ? vb1 + hh * 8192 : vb0 + hh * vhs) + (lane & 15) * 64;
#pragma unroll
              for (int dp = 0; dp < 2; dp++) {
                uint32_t b0, b1, b2, b3;
                ldsm_x4_t(va + ((dp * 32 + lhi) ^ lsw2), b0, b1, b2, b3);
                mma_bf16(o[hh][dp * 2], pa0, pa1, pa2, pa3, b0, b1);
                mma_bf16(o[hh][dp * 2 + 1], pa0, pa1, pa2, pa3, b2, b3);
              }
            }
          }
#pragma unroll
          for (int hh = 0; hh < 2; hh++)
#pragma unroll
            for (int dp = 0; dp < 2; dp++)
              stsm_x4(qb + ((hh * 64 + dp * 32 + lhi) ^ lsw), pack_bf16(o[hh][dp * 2][0], o[hh][dp * 2][1]), pack_bf16(o[hh][dp * 2][2], o[hh][dp * 2][3]),
                      pack_bf16(o[hh][dp * 2 + 1][0], o[hh][dp * 2 + 1][1]), pack_bf16(o[hh][dp * 2 + 1][2], o[hh][dp * 2 + 1][3]));
          if (hp == 0) { fence_proxy_async_smem(); bar_arrive<BAR_O, 288>(); }
        }
      } else {
        float p0[32], p1[32];
        PHI_LOAD(acckv, csa + 512);
        float4* kvg = reinterpret_cast<float4*>(g_kv[l >> 1] + (jj * 4 + wg * 2) * KVH) + (tid & 127);
        const float c0 = rs0 * LOG2E, c1 = rs1 * LOG2E;
        const uint32_t dst = ((t & 2) ? pQ0 : pK0) + (t & 1) * SLOT + (r0 + g) * 128;
        const uint32_t dsw = (uint32_t)(g ^ (2 * t)) << 4;
#pragma unroll 1
        for (int it = 0; it < 2; it++) {
          float e[32];
          float mn0 = rmin32(p0);
          asm volatile("" : "+f"(mn0)); SCHED_FENCE();
          float ia = exps32(e, p0, -c0, mn0 * c0), mx0 = rmax32(p0), mn1 = rmin32(p1);
          asm volatile("" : "+f"(ia), "+f"(mx0), "+f"(mn1)); PIN32(e);
          if (it == 0) mbar_wait(bar_done + 15 * 8, 0);
          else bar_sync<BAR_CONS, 256>();
          SCHED_FENCE();
          store32(e, ia, dst, dsw, 4);
          float ib = exps32(p0, p0, c0, -mx0 * c0);
          asm volatile("" : "+f"(ib)); PIN32(p0); SCHED_FENCE();
          store32(p0, ib, dst, dsw, 0);
          float ic = exps32(e, p1, -c1, mn1 * c1), mx1 = rmax32(p1);
          asm volatile("" : "+f"(ic), "+f"(mx1)); PIN32(e); SCHED_FENCE();
          store32(e, ic, dst + 1024, dsw, 4);
          float id = exps32(p1, p1, c1, -mx1 * c1);
          asm volatile("" : "+f"(id)); PIN32(p1); SCHED_FENCE();
          store32(p1, id, dst + 1024, dsw, 0);
          if (it == 0) {
            if (tid < 64) sts128(sbase + 10 * SLOT + tid * 16, 0x3F803F80u, 0x3F803F80u, 0x3F803F80u, 0x3F803F80u);
            fence_proxy_async_smem();
            bar_sync<BAR_CONS, 256>();
            PROF(6 + l * 16);
            float kv0[20], kv1[20];
            ACC_DEF(kv0, 20); ACC_DEF(kv1, 20);
            const uint64_t dp0 = make_desc(wg ? pQ0 : pK0, 16, 1024);
            const uint64_t dv = (make_desc(pV0 + wg * SLOT, (3 - wg) * SLOT, 512) ^ (3ull << 62));
            constexpr uint64_t DVS = 64ull - (64ull << 16);
            wgmma_fence();
#pragma unroll
            for (int ks = 0; ks < 8; ks++) { if (ks == 0) wgmma_n40<0, 1>(kv0, dp0, dv); else wgmma_n40<1, 1>(kv0, dp0 + ks * 128, dv + ks * DVS); }
            wgmma_commit();
#pragma unroll
            for (int ks = 0; ks < 8; ks++) { if (ks == 0) wgmma_n40<0, 1>(kv1, dp0 + 1024, dv + 8 * DVS); else wgmma_n40<1, 1>(kv1, dp0 + 1024 + ks * 128, dv + (8 + ks) * DVS); }
            wgmma_commit();
            wgmma_wait<1>();
            ACC_FENCE(kv0, 20);
#pragma unroll
            for (int i = 0; i < 5; i++) red_v4(reinterpret_cast<float*>(kvg + i * 128), kv0[i * 4], kv0[i * 4 + 1], kv0[i * 4 + 2], kv0[i * 4 + 3]);
            PHI_LOAD(accq, csa);
            PIN32(p0); PIN32(p1);
            wgmma_wait<0>();
            ACC_FENCE(kv1, 20);
            PROF(70 + l);
#pragma unroll
            for (int i = 0; i < 5; i++) red_v4(reinterpret_cast<float*>(kvg + 640 + i * 128), kv1[i * 4], kv1[i * 4 + 1], kv1[i * 4 + 2], kv1[i * 4 + 3]);
            bar_arrive<BAR_KV, 288>();
            PROF(7 + l * 16);
          }
        }
        PROF(8 + l * 16);
        {
          if (lane == 0) wait_flag(&g_flags.kvready[l >> 1][jj].v, ep1 * 16);
          __syncwarp();
          PROF(9 + l * 16);
          float4 v[10];
#pragma unroll
          for (int i = 0; i < 10; i++) v[i] = __ldcg(kvg + i * 128);
          const uint32_t dst = pV0 + wg * SLOT + ((warp & 3) * 16 + (lane & 15)) * 128;
#pragma unroll
          for (int i = 0; i < 4; i++) {
            const float4 a = v[(i >> 1) * 5 + (i & 1) * 2], b = v[(i >> 1) * 5 + (i & 1) * 2 + 1];
            stsm_x4(dst + (i >> 1) * 8192 + (((i & 1) * 32 + lhi) ^ lsw), pack_bf16(a.x, a.y), pack_bf16(a.z, a.w), pack_bf16(b.x, b.y), pack_bf16(b.z, b.w));
          }
          stsm_x4(dst + (lane >> 4) * 8192 + (64u ^ lsw), pack_bf16(v[4].x, v[4].y), pack_bf16(v[4].z, v[4].w), pack_bf16(v[9].x, v[9].y), pack_bf16(v[9].z, v[9].w));
        }
        fence_proxy_async_smem();
        bar_sync<BAR_CONS, 256>();
        PROF(10 + l * 16);
        float o[4][20];
        ACC_DEF(o[0], 20); ACC_DEF(o[1], 20); ACC_DEF(o[2], 20); ACC_DEF(o[3], 20);
        wgmma_fence();
#pragma unroll
        for (int hh = 0; hh < 4; hh++) {
          const int h = hh ^ 2;
          const uint64_t da = make_desc((h < 2 ? pK0 : pQ0) + (h & 1) * SLOT + wg * 8192, 16, 1024);
          const uint64_t db = make_desc(pV0 + h * 8192, 16, 1024);
#pragma unroll
          for (int ks = 0; ks < 4; ks++) { if (ks == 0) wgmma_n40<0, 0>(o[h], da, db); else wgmma_n40<1, 0>(o[h], da + ks * 2, db + ks * 128); }
          if (hh & 1) wgmma_commit();
        }
        uint32_t ow[4][8];
#pragma unroll
        for (int hh = 0; hh < 4; hh++) {
          const int h = hh ^ 2;
          if (hh == 0) { wgmma_wait<1>(); ACC_FENCE(o[2], 20); ACC_FENCE(o[3], 20); }
          if (hh == 2) { bar_wg(wg); wgmma_wait<0>(); ACC_FENCE(o[0], 20); ACC_FENCE(o[1], 20); }
          const float i0 = rcp_fast(o[h][16] + 1e-6f), i1 = rcp_fast(o[h][18] + 1e-6f);
#pragma unroll
          for (int i = 0; i < 4; i++) {
            ow[h][2 * i] = pack_bf16(o[h][i * 4] * i0, o[h][i * 4 + 1] * i0);
            ow[h][2 * i + 1] = pack_bf16(o[h][i * 4 + 2] * i1, o[h][i * 4 + 3] * i1);
          }
        }
#pragma unroll
        for (int h = 0; h < 4; h++) {
          const uint32_t ob = pQ0 + (h >> 1) * SLOT + srowoff;
#pragma unroll
          for (int dp = 0; dp < 2; dp++)
            stsm_x4(ob + (((h & 1) * 64 + dp * 32 + lhi) ^ lsw), ow[h][dp * 4], ow[h][dp * 4 + 1], ow[h][dp * 4 + 2], ow[h][dp * 4 + 3]);
          if (h == 1) { fence_proxy_async_smem(); bar_arrive<BAR_O, 288>(); }
        }
      }
      fence_proxy_async_smem();
      bar_arrive<BAR_O1, 288>();
      if (lane < 2) mbar_arrive_remote(bar_epi, lane);
      if (l == 0 && NLAYERS > 1) {
        PROF(74);
        mbar_wait(bar_x0, 0);
        const uint32_t wb = sbase + (warp & 1) * 3 * SLOT + (warp >> 1) * 2048;
        uint32_t w[2][2][2][4];
#pragma unroll
        for (int h = 0; h < 4; h++) {
          uint32_t af[2][2][4];
#pragma unroll
          for (int i = 0; i < 4; i++)
            ldsm_x4_t(sbase + 10 * SLOT + 8192 + h * 2048 + ((i & 1) * 16 + (lane >> 4) * 8 + (lane & 7)) * 64 + (((i >> 1) * 32 + ((lane >> 3) & 1) * 16) ^ lsw2),
                      af[i >> 1][i & 1][0], af[i >> 1][i & 1][1], af[i >> 1][i & 1][2], af[i >> 1][i & 1][3]);
#pragma unroll
          for (int i = 0; i < 2; i++) {
            uint32_t b0, b1, b2, b3;
            ldsm_x4(wb + (h >> 1) * 8192 + i * 1024 + (lane & 7) * 128 + (((h & 1) * 64 + ((lane >> 3) << 4)) ^ lsw), b0, b1, b2, b3);
            float c0[4] = {0.f, 0.f, 0.f, 0.f}, c1[4] = {0.f, 0.f, 0.f, 0.f};
            mma_bf16(c0, af[0][0][0], af[0][0][1], af[0][0][2], af[0][0][3], b0, b1);
            mma_bf16(c1, af[1][0][0], af[1][0][1], af[1][0][2], af[1][0][3], b0, b1);
            mma_bf16(c0, af[0][1][0], af[0][1][1], af[0][1][2], af[0][1][3], b2, b3);
            mma_bf16(c1, af[1][1][0], af[1][1][1], af[1][1][2], af[1][1][3], b2, b3);
            w[i][0][0][h] = pack_bf16(c0[0], c0[2]); w[i][0][1][h] = pack_bf16(c1[0], c1[2]);
            w[i][1][0][h] = pack_bf16(c0[1], c0[3]); w[i][1][1][h] = pack_bf16(c1[1], c1[3]);
          }
        }
        __syncwarp();
#pragma unroll
        for (int i = 0; i < 8; i++) {
          const uint32_t (&q)[4] = w[i >> 2][(i >> 1) & 1][i & 1];
          const uint32_t rr = 2 * t + ((i >> 1) & 1);
          sts128(wb + (g >> 2) * 8192 + ((i >> 2) * 8 + rr) * 128 + (((((2 * g) & 7) + (i & 1)) ^ rr) << 4), q[0], q[1], q[2], q[3]);
        }
        fence_proxy_async_smem();
        PROF(75);
        bar_arrive<BAR_WF, 288>();
      }
      PROF(11 + l * 16);
      {
        float acc[64];
        LOAD_X();
        ACC_FENCE(acc, 64);
        bar_wg(wg);
#pragma unroll 1
        for (int s = 0; s < 16; s++) {
          const uint64_t da = make_desc(sbase + (uint32_t)((WO_ASLOT >> (4 * s)) & 15) * SLOT + wg * 8192, 16, 1024);
          const uint64_t db = make_desc(sbase + (uint32_t)((WO_BSLOT >> (4 * s)) & 15) * SLOT, 8192, 1024);
          mbar_wait(bar_full + s * 8, 1);
          if (s == 0) PROF(12 + l * 16);
          if (s == 2) PROF(13 + l * 16);
          wgmma_fence();
#pragma unroll
          for (int k4 = 0; k4 < 4; k4++) wgmma_n128<1>(acc, da + k4 * 2, db + k4 * 128);
          wgmma_commit();
          if (s > 0) { wgmma_wait<1>(); if (lane < 2) mbar_arrive_remote(bar_done + (s - 1) * 8, lane); }
        }
        wgmma_wait<0>();
        ACC_FENCE(acc, 64);
        if (lane < 2) mbar_arrive_remote(bar_done + 15 * 8, lane);
        PROF(14 + l * 16);
#pragma unroll
        for (int j = 0; j < 8; j++) {
          stsm_x4(pX0 + (j >> 2) * SLOT + srowoff + ((((uint32_t)(j & 3) << 5) + lhi) ^ lsw),
                  pack_bf16(acc[j * 8 + 0], acc[j * 8 + 1]), pack_bf16(acc[j * 8 + 2], acc[j * 8 + 3]),
                  pack_bf16(acc[j * 8 + 4], acc[j * 8 + 5]), pack_bf16(acc[j * 8 + 6], acc[j * 8 + 7]));
          if (j == 3) { fence_proxy_async_smem(); bar_arrive<BAR_X, 288>(); }
        }
        fence_proxy_async_smem();
        bar_arrive<BAR_X1, 288>();
        PROF(15 + l * 16);
      }
    }
    if (tid == 0) {
      unsigned old = atomicAdd(&g_flags.done.v, 1);
      if (old == ep1 * NMAIN - 1) {
        asm volatile("st.relaxed.gpu.global.u32 [%0], %1;" :: "l"(&g_flags.epoch.v), "r"(ep1) : "memory");
      }
    }
    __syncwarp();
    cluster_sync();
  }
}

typedef CUresult (*PFN_encode)(CUtensorMap*, CUtensorMapDataType, cuuint32_t, void*, const cuuint64_t*, const cuuint64_t*,
                               const cuuint32_t*, const cuuint32_t*, CUtensorMapInterleave, CUtensorMapSwizzle,
                               CUtensorMapL2promotion, CUtensorMapFloatOOBfill);

CUtensorMap make_map(PFN_encode enc, const void* ptr, uint64_t inner, uint64_t outer, uint32_t box_inner, uint32_t box_outer,
                     CUtensorMapSwizzle swz = CU_TENSOR_MAP_SWIZZLE_128B) {
  CUtensorMap m;
  cuuint64_t dims[2] = {inner, outer};
  cuuint64_t strides[1] = {inner * 2};
  cuuint32_t box[2] = {box_inner, box_outer};
  cuuint32_t es[2] = {1, 1};
  enc(&m, CU_TENSOR_MAP_DATA_TYPE_BFLOAT16, 2, const_cast<void*>(ptr), dims, strides, box, es, CU_TENSOR_MAP_INTERLEAVE_NONE,
      swz, CU_TENSOR_MAP_L2_PROMOTION_L2_256B, CU_TENSOR_MAP_FLOAT_OOB_FILL_NONE);
  return m;
}

}

extern "C" void kernel_launch(void* const* d_in, const int* in_sizes, int n_in, void* d_out, int out_size) {
  (void)in_sizes; (void)n_in; (void)out_size;
  static PFN_encode enc = nullptr;
  if (!enc) {
    void* fn = nullptr;
    cudaDriverEntryPointQueryResult qr;
    cudaGetDriverEntryPoint("cuTensorMapEncodeTiled", &fn, cudaEnableDefault, &qr);
    enc = (PFN_encode)fn;
    cudaFuncSetAttribute(mega_kernel, cudaFuncAttributeMaxDynamicSharedMemorySize, SMEM_BYTES);
  }
  Params prm;
  prm.x0 = (const __nv_bfloat16*)d_in[0];
  prm.wA_qkv = (const __nv_bfloat16*)d_in[1];
  prm.wA_o = (const __nv_bfloat16*)d_in[2];
  prm.wB_qkv = (const __nv_bfloat16*)d_in[4];
  prm.wB_phi = (const __nv_bfloat16*)d_in[5];
  prm.wB_o = (const __nv_bfloat16*)d_in[6];
  prm.out = (__nv_bfloat16*)d_out;
  void *obuf = nullptr, *wf = nullptr;
  cudaGetSymbolAddress(&obuf, g_obuf);
  cudaGetSymbolAddress(&wf, g_wfold);
  CUtensorMap tm_x0 = make_map(enc, d_in[0], D_MODEL, S_LEN, 64, 128);
  CUtensorMap tm_xo = make_map(enc, d_out, D_MODEL, S_LEN, 64, 128);
  CUtensorMap tm_o = make_map(enc, obuf, D_MODEL, S_LEN, 64, 128);
  CUtensorMap tm_wf = make_map(enc, wf, 2048, D_MODEL, 64, 64);
  CUtensorMap tm_wqA = make_map(enc, d_in[1], 3 * D_MODEL, D_MODEL, 64, 64);
  CUtensorMap tm_wqB = make_map(enc, prm.wB_qkv, 3 * D_MODEL, D_MODEL, 64, 64);
  CUtensorMap tm_woA = make_map(enc, prm.wA_o, D_MODEL, D_MODEL, 64, 64);
  CUtensorMap tm_woB = make_map(enc, prm.wB_o, D_MODEL, D_MODEL, 64, 64);
  CUtensorMap tm_phi = make_map(enc, prm.wB_phi, 32, 1024, 32, 128, CU_TENSOR_MAP_SWIZZLE_64B);
  mega_kernel<<<NMAIN + NAUX, 384, SMEM_BYTES>>>(tm_x0, tm_xo, tm_o, tm_wf, tm_wqA, tm_wqB, tm_woA, tm_woB, tm_phi, prm);
}
```

```cpp
#include <cuda_runtime.h>
#include <cuda.h>
#include <cuda_bf16.h>
#include <stdint.h>

#define NLAYERS 4

#define STAG1 300
#define HPUMP1 2
#define HPUMP2 2
#define ASKEW 2
#define BMASK 0x1FF
#define ASITE 1
namespace {

constexpr int S_LEN = 2048, D_MODEL = 1024;
constexpr int NAUX = 4, NMAIN = 128;
constexpr int SLOT = 16384;
constexpr int QST = 24576;
constexpr int OFF_RA = 6 * SLOT, OFF_S = 10 * SLOT;
constexpr int OFF_HALO = 13 * SLOT, OFF_ONES = OFF_HALO + 4096, OFF_LNA = OFF_HALO + 5120, OFF_LNB = OFF_HALO + 7168;
constexpr int OFF_BAR = 14 * SLOT;
constexpr int OFF_ST = OFF_BAR + 1024;
constexpr int SMEM_BYTES = OFF_ST + 512;
constexpr unsigned long long WO_ASLOT = 0x98C76BA398C7698Cull;
constexpr unsigned long long WO_BSLOT = 0x5432105421054210ull;
__device__ __forceinline__ int kslice(int j, int i) { return i < 2 ? 2 * j + i : (i < 9 ? 2 * ((j + i - 1) & 7) : 2 * ((j + i) & 7) + 1); }
__device__ __forceinline__ int wslice(int j, int s) { return 2 * ((j + s) & 7) + (s >> 3); }
constexpr int KVH = 5 * 128 * 4;

struct __align__(128) Flag { unsigned v; unsigned pad[31]; };
struct Flags {
  Flag xready[4][16][2];
  Flag oready[4][16][2];
  Flag kvready[2][8][2];
  Flag wfready[8];
  Flag done;
  Flag epoch;
};

__device__ Flags g_flags;
__device__ __nv_bfloat16 g_obuf[S_LEN * D_MODEL];
__device__ __nv_bfloat16 g_wfold[D_MODEL * 2048];
__device__ uint4 g_halo[16 * 8 * 512];
__device__ float g_kv[2][32 * KVH];
__device__ uint4 g_colsum[2][2][1536];
__device__ __align__(128) uint2 g_stats[S_LEN * 8];
#define STAT_TAG(l) ((ep1 * NLAYERS + (l) + 1) & 3u)

#define PROFT(i) do {} while (0)
#define PROF(i) do {} while (0)

__device__ __forceinline__ uint32_t smem_u32(const void* p) { return (uint32_t)__cvta_generic_to_shared(p); }
__device__ __forceinline__ bool elect_one() {
  uint32_t p;
  asm volatile("{\n.reg .pred p;\nelect.sync _|p, 0xffffffff;\nselp.u32 %0, 1, 0, p;\n}\n" : "=r"(p));
  return p != 0;
}
__device__ __forceinline__ void mbar_init(uint32_t bar, uint32_t cnt) {
  asm volatile("mbarrier.init.shared::cta.b64 [%0], %1;" :: "r"(bar), "r"(cnt));
}
__device__ __forceinline__ void mbar_expect_tx(uint32_t bar, uint32_t bytes) {
  asm volatile("mbarrier.arrive.expect_tx.shared::cta.b64 _, [%0], %1;" :: "r"(bar), "r"(bytes) : "memory");
}
__device__ __forceinline__ void mbar_wait(uint32_t bar, uint32_t parity) {
  uint32_t ok;
  int it = 0;
  do {
    asm volatile("{\n.reg .pred p;\nmbarrier.try_wait.parity.shared::cta.b64 p, [%1], %2;\nselp.u32 %0, 1, 0, p;\n}\n"
                 : "=r"(ok) : "r"(bar), "r"(parity) : "memory");
  } while (!ok && ++it < (1 << 20));
}
__device__ __forceinline__ void mbar_wait_sl(uint32_t bar, uint32_t parity) {
  uint32_t ok;
  int it = 0;
  do {
    asm volatile("{\n.reg .pred p;\nmbarrier.try_wait.parity.shared::cta.b64 p, [%1], %2, %3;\nselp.u32 %0, 1, 0, p;\n}\n"
                 : "=r"(ok) : "r"(bar), "r"(parity), "r"(20000) : "memory");
  } while (!ok && ++it < (1 << 16));
}
__device__ __forceinline__ void mbar_arrive_local(uint32_t bar) {
  asm volatile("mbarrier.arrive.shared::cta.b64 _, [%0];" :: "r"(bar) : "memory");
}
__device__ __forceinline__ void mbar_arrive_remote(uint32_t bar, uint32_t cta_rank) {
  asm volatile("{\n.reg .b32 ra;\nmapa.shared::cluster.u32 ra, %0, %1;\nmbarrier.arrive.shared::cluster.b64 _, [ra];\n}\n"
               :: "r"(bar), "r"(cta_rank) : "memory");
}
__device__ __forceinline__ void tma_load_2d(uint32_t dst, const CUtensorMap* tm, uint32_t bar, int c0, int c1) {
  asm volatile("cp.async.bulk.tensor.2d.shared::cluster.global.mbarrier::complete_tx::bytes [%0], [%1, {%3, %4}], [%2];"
               :: "r"(dst), "l"(tm), "r"(bar), "r"(c0), "r"(c1) : "memory");
}
__device__ __forceinline__ void tma_load_2d_mc(uint32_t dst, const CUtensorMap* tm, uint32_t bar, int c0, int c1) {
  asm volatile("cp.async.bulk.tensor.2d.shared::cluster.global.mbarrier::complete_tx::bytes.multicast::cluster [%0], [%1, {%3, %4}], [%2], %5;"
               :: "r"(dst), "l"(tm), "r"(bar), "r"(c0), "r"(c1), "h"((uint16_t)3) : "memory");
}
__device__ __forceinline__ void tma_store_2d(const CUtensorMap* tm, uint32_t src, int c0, int c1) {
  asm volatile("cp.async.bulk.tensor.2d.global.shared::cta.bulk_group [%0, {%2, %3}], [%1];"
               :: "l"(tm), "r"(src), "r"(c0), "r"(c1) : "memory");
}
__device__ __forceinline__ void bulk_commit_wait() {
  asm volatile("cp.async.bulk.commit_group;\ncp.async.bulk.wait_group 0;" ::: "memory");
}
__device__ __forceinline__ void prefetch_l2(const void* p, uint32_t bytes) {
  asm volatile("cp.async.bulk.prefetch.L2.global [%0], %1;" :: "l"(p), "r"(bytes) : "memory");
}
__device__ __forceinline__ void prefetch_tmap(const CUtensorMap* tm) {
  asm volatile("prefetch.tensormap [%0];" :: "l"(tm) : "memory");
}
__device__ __forceinline__ void fence_proxy_async_global() { asm volatile("fence.proxy.async.global;" ::: "memory"); }
__device__ __forceinline__ void fence_proxy_async_smem() { asm volatile("fence.proxy.async.shared::cta;" ::: "memory"); }
__device__ __forceinline__ unsigned ld_relaxed(const unsigned* p) {
  unsigned v;
  asm volatile("ld.relaxed.gpu.global.u32 %0, [%1];" : "=r"(v) : "l"(p) : "memory");
  return v;
}
__device__ __forceinline__ void fence_acquire() { asm volatile("fence.acquire.gpu;" ::: "memory"); }
__device__ __forceinline__ void wait_flag(const unsigned* p, unsigned target) {
  int it = 0;
  while ((int)(ld_relaxed(p) - target) < 0 && ++it < (1 << 20)) {}
  fence_acquire();
}
__device__ __forceinline__ void wait_flag_fast(const unsigned* p, unsigned target) {
  unsigned v0 = ld_relaxed(p);
  __nanosleep(100);
  unsigned v1 = ld_relaxed(p);
  __nanosleep(100);
  unsigned v2 = ld_relaxed(p);
  for (int it = 0; it < (1 << 19); it++) {
    if ((int)(v0 - target) >= 0) break;
    v0 = ld_relaxed(p);
    if ((int)(v1 - target) >= 0) break;
    v1 = ld_relaxed(p);
    if ((int)(v2 - target) >= 0) break;
    v2 = ld_relaxed(p);
  }
  fence_acquire();
}
__device__ __forceinline__ void signal_release(unsigned* p) {
  asm volatile("red.release.gpu.global.add.u32 [%0], 1;" :: "l"(p) : "memory");
}
template <int ID, int N> __device__ __forceinline__ void bar_arrive() { asm volatile("bar.arrive %0, %1;" :: "n"(ID), "n"(N) : "memory"); }
template <int ID, int N> __device__ __forceinline__ void bar_sync() { asm volatile("bar.sync %0, %1;" :: "n"(ID), "n"(N) : "memory"); }
__device__ __forceinline__ void bar_wg(int wg) { asm volatile("bar.sync %0, 128;" :: "r"(2 + wg) : "memory"); }
__device__ __forceinline__ void cluster_sync() {
  asm volatile("barrier.cluster.arrive.relaxed.aligned;\nbarrier.cluster.wait.aligned;" ::: "memory");
}
__device__ __forceinline__ void cluster_wait() { asm volatile("barrier.cluster.wait.acquire.aligned;" ::: "memory"); }
enum { BAR_KV = 4  , BAR_O = 7  , BAR_WF = 12, BAR_SKEW = 13 };

__device__ __forceinline__ void wgmma_fence() { asm volatile("wgmma.fence.sync.aligned;" ::: "memory"); }
__device__ __forceinline__ void wgmma_commit() { asm volatile("wgmma.commit_group.sync.aligned;" ::: "memory"); }
template <int N> __device__ __forceinline__ void wgmma_wait() { asm volatile("wgmma.wait_group.sync.aligned %0;" :: "n"(N) : "memory"); }

template <int scale_d, int tnsp_b = 1> __device__ __forceinline__ void wgmma_n192(float* d, uint64_t descA, uint64_t descB) {
  asm volatile("{\n.reg .pred p;\nsetp.ne.b32 p, %98, 0;\n"
               "wgmma.mma_async.sync.aligned.m64n192k16.f32.bf16.bf16 {%0,%1,%2,%3,%4,%5,%6,%7,%8,%9,%10,%11,%12,%13,%14,%15,%16,%17,%18,%19,%20,%21,%22,%23,%24,%25,%26,%27,%28,%29,%30,%31,%32,%33,%34,%35,%36,%37,%38,%39,%40,%41,%42,%43,%44,%45,%46,%47,%48,%49,%50,%51,%52,%53,%54,%55,%56,%57,%58,%59,%60,%61,%62,%63,%64,%65,%66,%67,%68,%69,%70,%71,%72,%73,%74,%75,%76,%77,%78,%79,%80,%81,%82,%83,%84,%85,%86,%87,%88,%89,%90,%91,%92,%93,%94,%95}, %96, %97, p, 1, 1, 0, %99;\n}\n"
               : "+f"(d[0]), "+f"(d[1]), "+f"(d[2]), "+f"(d[3]), "+f"(d[4]), "+f"(d[5]), "+f"(d[6]), "+f"(d[7]), "+f"(d[8]), "+f"(d[9]), "+f"(d[10]), "+f"(d[11]), "+f"(d[12]), "+f"(d[13]), "+f"(d[14]), "+f"(d[15]), "+f"(d[16]), "+f"(d[17]), "+f"(d[18]), "+f"(d[19]), "+f"(d[20]), "+f"(d[21]), "+f"(d[22]), "+f"(d[23]), "+f"(d[24]), "+f"(d[25]), "+f"(d[26]), "+f"(d[27]), "+f"(d[28]), "+f"(d[29]), "+f"(d[30]), "+f"(d[31]), "+f"(d[32]), "+f"(d[33]), "+f"(d[34]), "+f"(d[35]), "+f"(d[36]), "+f"(d[37]), "+f"(d[38]), "+f"(d[39]), "+f"(d[40]), "+f"(d[41]), "+f"(d[42]), "+f"(d[43]), "+f"(d[44]), "+f"(d[45]), "+f"(d[46]), "+f"(d[47]), "+f"(d[48]), "+f"(d[49]), "+f"(d[50]), "+f"(d[51]), "+f"(d[52]), "+f"(d[53]), "+f"(d[54]), "+f"(d[55]), "+f"(d[56]), "+f"(d[57]), "+f"(d[58]), "+f"(d[59]), "+f"(d[60]), "+f"(d[61]), "+f"(d[62]), "+f"(d[63]), "+f"(d[64]), "+f"(d[65]), "+f"(d[66]), "+f"(d[67]), "+f"(d[68]), "+f"(d[69]), "+f"(d[70]), "+f"(d[71]), "+f"(d[72]), "+f"(d[73]), "+f"(d[74]), "+f"(d[75]), "+f"(d[76]), "+f"(d[77]), "+f"(d[78]), "+f"(d[79]), "+f"(d[80]), "+f"(d[81]), "+f"(d[82]), "+f"(d[83]), "+f"(d[84]), "+f"(d[85]), "+f"(d[86]), "+f"(d[87]), "+f"(d[88]), "+f"(d[89]), "+f"(d[90]), "+f"(d[91]), "+f"(d[92]), "+f"(d[93]), "+f"(d[94]), "+f"(d[95])
               : "l"(descA), "l"(descB), "n"(scale_d), "n"(tnsp_b));
}
template <int scale_d> __device__ __forceinline__ void wgmma_n128(float* d, uint64_t descA, uint64_t descB) {
  asm volatile("{\n.reg .pred p;\nsetp.ne.b32 p, %66, 0;\n"
               "wgmma.mma_async.sync.aligned.m64n128k16.f32.bf16.bf16 {%0,%1,%2,%3,%4,%5,%6,%7,%8,%9,%10,%11,%12,%13,%14,%15,%16,%17,%18,%19,%20,%21,%22,%23,%24,%25,%26,%27,%28,%29,%30,%31,%32,%33,%34,%35,%36,%37,%38,%39,%40,%41,%42,%43,%44,%45,%46,%47,%48,%49,%50,%51,%52,%53,%54,%55,%56,%57,%58,%59,%60,%61,%62,%63}, %64, %65, p, 1, 1, 0, 1;\n}\n"
               : "+f"(d[0]), "+f"(d[1]), "+f"(d[2]), "+f"(d[3]), "+f"(d[4]), "+f"(d[5]), "+f"(d[6]), "+f"(d[7]), "+f"(d[8]), "+f"(d[9]), "+f"(d[10]), "+f"(d[11]), "+f"(d[12]), "+f"(d[13]), "+f"(d[14]), "+f"(d[15]), "+f"(d[16]), "+f"(d[17]), "+f"(d[18]), "+f"(d[19]), "+f"(d[20]), "+f"(d[21]), "+f"(d[22]), "+f"(d[23]), "+f"(d[24]), "+f"(d[25]), "+f"(d[26]), "+f"(d[27]), "+f"(d[28]), "+f"(d[29]), "+f"(d[30]), "+f"(d[31]), "+f"(d[32]), "+f"(d[33]), "+f"(d[34]), "+f"(d[35]), "+f"(d[36]), "+f"(d[37]), "+f"(d[38]), "+f"(d[39]), "+f"(d[40]), "+f"(d[41]), "+f"(d[42]), "+f"(d[43]), "+f"(d[44]), "+f"(d[45]), "+f"(d[46]), "+f"(d[47]), "+f"(d[48]), "+f"(d[49]), "+f"(d[50]), "+f"(d[51]), "+f"(d[52]), "+f"(d[53]), "+f"(d[54]), "+f"(d[55]), "+f"(d[56]), "+f"(d[57]), "+f"(d[58]), "+f"(d[59]), "+f"(d[60]), "+f"(d[61]), "+f"(d[62]), "+f"(d[63])
               : "l"(descA), "l"(descB), "n"(scale_d));
}
template <int scale_d, int tnsp_a> __device__ __forceinline__ void wgmma_n40(float* d, uint64_t descA, uint64_t descB) {
  asm volatile("{\n.reg .pred p;\nsetp.ne.b32 p, %22, 0;\n"
               "wgmma.mma_async.sync.aligned.m64n40k16.f32.bf16.bf16 {%0,%1,%2,%3,%4,%5,%6,%7,%8,%9,%10,%11,%12,%13,%14,%15,%16,%17,%18,%19}, %20, %21, p, 1, 1, %23, 1;\n}\n"
               : "+f"(d[0]), "+f"(d[1]), "+f"(d[2]), "+f"(d[3]), "+f"(d[4]), "+f"(d[5]), "+f"(d[6]), "+f"(d[7]), "+f"(d[8]), "+f"(d[9]), "+f"(d[10]), "+f"(d[11]), "+f"(d[12]), "+f"(d[13]), "+f"(d[14]), "+f"(d[15]), "+f"(d[16]), "+f"(d[17]), "+f"(d[18]), "+f"(d[19])
               : "l"(descA), "l"(descB), "n"(scale_d), "n"(tnsp_a));
}
__device__ __forceinline__ uint64_t make_desc(uint32_t addr, uint32_t lbo_bytes, uint32_t sbo_bytes) {
  return (uint64_t)((addr & 0x3FFFF) >> 4) | ((uint64_t)(lbo_bytes >> 4) << 16) | ((uint64_t)(sbo_bytes >> 4) << 32) | (1ull << 62);
}

__device__ __forceinline__ void ldsm_x4(uint32_t addr, uint32_t& r0, uint32_t& r1, uint32_t& r2, uint32_t& r3) {
  asm volatile("ldmatrix.sync.aligned.m8n8.x4.shared.b16 {%0,%1,%2,%3}, [%4];" : "=r"(r0), "=r"(r1), "=r"(r2), "=r"(r3) : "r"(addr) : "memory");
}
__device__ __forceinline__ void ldsm_x4_t(uint32_t addr, uint32_t& r0, uint32_t& r1, uint32_t& r2, uint32_t& r3) {
  asm volatile("ldmatrix.sync.aligned.m8n8.x4.trans.shared.b16 {%0,%1,%2,%3}, [%4];" : "=r"(r0), "=r"(r1), "=r"(r2), "=r"(r3) : "r"(addr) : "memory");
}
__device__ __forceinline__ void stsm_x4(uint32_t addr, uint32_t r0, uint32_t r1, uint32_t r2, uint32_t r3) {
  asm volatile("stmatrix.sync.aligned.m8n8.x4.shared.b16 [%0], {%1,%2,%3,%4};" :: "r"(addr), "r"(r0), "r"(r1), "r"(r2), "r"(r3) : "memory");
}
__device__ __forceinline__ void sts128(uint32_t addr, uint32_t a, uint32_t b, uint32_t c, uint32_t d) {
  asm volatile("st.shared.v4.u32 [%0], {%1,%2,%3,%4};" :: "r"(addr), "r"(a), "r"(b), "r"(c), "r"(d) : "memory");
}
__device__ __forceinline__ float lds32f(uint32_t addr) {
  float v;
  asm volatile("ld.shared.f32 %0, [%1];" : "=f"(v) : "r"(addr) : "memory");
  return v;
}
__device__ __forceinline__ void sts32f(uint32_t addr, float a) {
  asm volatile("st.shared.f32 [%0], %1;" :: "r"(addr), "f"(a) : "memory");
}
__device__ __forceinline__ void mma_bf16(float (&c)[4], uint32_t a0, uint32_t a1, uint32_t a2, uint32_t a3, uint32_t b0, uint32_t b1) {
  asm volatile("mma.sync.aligned.m16n8k16.row.col.f32.bf16.bf16.f32 {%0,%1,%2,%3}, {%4,%5,%6,%7}, {%8,%9}, {%0,%1,%2,%3};"
               : "+f"(c[0]), "+f"(c[1]), "+f"(c[2]), "+f"(c[3]) : "r"(a0), "r"(a1), "r"(a2), "r"(a3), "r"(b0), "r"(b1));
}
__device__ __forceinline__ uint32_t pack_bf16(float lo, float hi) {
  uint32_t r;
  asm("cvt.rn.bf16x2.f32 %0, %1, %2;" : "=r"(r) : "f"(hi), "f"(lo));
  return r;
}
__device__ __forceinline__ float bf_lo(uint32_t v) { return __uint_as_float(v << 16); }
__device__ __forceinline__ float bf_hi(uint32_t v) { return __uint_as_float(v & 0xFFFF0000u); }
__device__ __forceinline__ void split3(float x, uint32_t& h, uint32_t& m, uint32_t& l) {
  h = pack_bf16(x, 0.f); x -= bf_lo(h);
  m = pack_bf16(x, 0.f); x -= bf_lo(m);
  l = pack_bf16(x, 0.f);
}
__device__ __forceinline__ float ex2(float x) { float r; asm("ex2.approx.ftz.f32 %0, %1;" : "=f"(r) : "f"(x)); return r; }
__device__ __forceinline__ float rcp_fast(float x) { float r; asm("rcp.approx.ftz.f32 %0, %1;" : "=f"(r) : "f"(x)); return r; }
__device__ __forceinline__ void red_v4(float* p, float a, float b, float c, float d) {
  asm volatile("red.global.add.v4.f32 [%0], {%1, %2, %3, %4};" :: "l"(p), "f"(a), "f"(b), "f"(c), "f"(d) : "memory");
}
__device__ __forceinline__ void st_ll(uint4* p, uint32_t d0, uint32_t d1, uint32_t tag) {
  asm volatile("{\n.reg .b64 a, b;\nmov.b64 a, {%1, %3};\nmov.b64 b, {%2, %3};\nst.relaxed.gpu.global.v2.b64 [%0], {a, b};\n}\n"
               :: "l"(p), "r"(d0), "r"(d1), "r"(tag) : "memory");
}
__device__ __forceinline__ uint4 ld_ll(const uint4* p) {
  uint4 v;
  asm volatile("{\n.reg .b64 a, b;\nld.relaxed.gpu.global.v2.b64 {a, b}, [%4];\nmov.b64 {%0, %1}, a;\nmov.b64 {%2, %3}, b;\n}\n"
               : "=r"(v.x), "=r"(v.y), "=r"(v.z), "=r"(v.w) : "l"(p) : "memory");
  return v;
}
__device__ __forceinline__ void st_b64(uint2* p, uint32_t a, uint32_t b) {
  asm volatile("{\n.reg .b64 v;\nmov.b64 v, {%1, %2};\nst.relaxed.gpu.global.b64 [%0], v;\n}\n" :: "l"(p), "r"(a), "r"(b) : "memory");
}
__device__ __forceinline__ void st_b128(uint4* p, uint32_t a, uint32_t b, uint32_t c, uint32_t d) {
  asm volatile("{\n.reg .b128 v;\nmov.b128 v, {%1, %2, %3, %4};\nst.relaxed.gpu.global.b128 [%0], v;\n}\n" :: "l"(p), "r"(a), "r"(b), "r"(c), "r"(d) : "memory");
}
__device__ __forceinline__ uint4 ld_b128(const uint4* p) {
  uint4 v;
  asm volatile("{\n.reg .b128 v;\nld.relaxed.gpu.global.b128 v, [%4];\nmov.b128 {%0, %1, %2, %3}, v;\n}\n" : "=r"(v.x), "=r"(v.y), "=r"(v.z), "=r"(v.w) : "l"(p) : "memory");
  return v;
}

constexpr float LOG2E = 1.4426950408889634f;

struct Params {
  const __nv_bfloat16* x0;
  const __nv_bfloat16* wA_qkv;
  const __nv_bfloat16* wA_o;
  const __nv_bfloat16* wB_qkv;
  const __nv_bfloat16* wB_phi;
  const __nv_bfloat16* wB_o;
  __nv_bfloat16* out;
};

#define ACC_DEF(d, n) _Pragma("unroll") for (int i_ = 0; i_ < (n); i_++) asm volatile("" : "=f"(d[i_]))
#define ACC_FENCE(d, n) _Pragma("unroll") for (int i_ = 0; i_ < (n); i_++) asm volatile("" : "+f"(d[i_]) :: "memory")
#define PIN(a, n) _Pragma("unroll") for (int i_ = 0; i_ < (n); i_++) asm volatile("" : "+f"((a)[i_]))
#define PINU(a, n) _Pragma("unroll") for (int i_ = 0; i_ < (n); i_++) asm volatile("" : "+r"((a)[i_]))

#define STAGE64(acc, off, p0, KIND) { \
    uint32_t w_[4][4]; \
    _Pragma("unroll") for (int j_ = 0; j_ < 4; j_++) { \
      const int o_ = (off) + j_ * 8; \
      w_[j_][0] = pack_bf16(rs0 * acc[o_ + 0], rs0 * acc[o_ + 1]); \
      w_[j_][1] = pack_bf16(rs1 * acc[o_ + 2], rs1 * acc[o_ + 3]); \
      w_[j_][2] = pack_bf16(rs0 * acc[o_ + 4], rs0 * acc[o_ + 5]); \
      w_[j_][3] = pack_bf16(rs1 * acc[o_ + 6], rs1 * acc[o_ + 7]); \
    } \
    if (hsend) { \
      _Pragma("unroll") for (int j_ = 0; j_ < 4; j_++) { \
        w_[j_][0] = (w_[j_][0] & ~1u) | hbit; \
        st_b128(hbase + lane + ((KIND) * 4 + j_) * 32, w_[j_][0], w_[j_][1], w_[j_][2], w_[j_][3]); \
      } \
    } \
    _Pragma("unroll") for (int j_ = 0; j_ < 4; j_++) \
      stsm_x4((KIND) ? (p0) + (j_ >> 1) * 8192 + (srowoff >> 1) + ((((uint32_t)(j_ & 1) << 5) + lhi) ^ lsw2) \
                     : (p0) + srowoff + ((((uint32_t)j_ << 5) + lhi) ^ lsw), \
              w_[j_][0], w_[j_][1], w_[j_][2], w_[j_][3]); \
  }
#define RW(j) (((j) >> 1) * 4 + ((j) & 1))
__device__ __forceinline__ float rmax16(const float* p) {
  float m[4];
#pragma unroll
  for (int j = 0; j < 4; j++) m[j] = fmaxf(fmaxf(p[RW(j)], p[RW(j + 4)]), fmaxf(p[RW(j + 8)], p[RW(j + 12)]));
  const float r = fmaxf(fmaxf(m[0], m[1]), fmaxf(m[2], m[3]));
  return fmaxf(r, __shfl_xor_sync(0xffffffffu, r, 1));
}
__device__ __forceinline__ float rmin16(const float* p) {
  float m[4];
#pragma unroll
  for (int j = 0; j < 4; j++) m[j] = fminf(fminf(p[RW(j)], p[RW(j + 4)]), fminf(p[RW(j + 8)], p[RW(j + 12)]));
  const float r = fminf(fminf(m[0], m[1]), fminf(m[2], m[3]));
  return fminf(r, __shfl_xor_sync(0xffffffffu, r, 1));
}
__device__ __forceinline__ float exps16(float* o, const float* p, float c, float b) {
  float s[4] = {0.f, 0.f, 0.f, 0.f};
#pragma unroll
  for (int j = 0; j < 16; j++) { o[j] = ex2(fmaf(p[RW(j)], c, b)); s[j & 3] += o[j]; }
  return (s[0] + s[1]) + (s[2] + s[3]);
}
__device__ __forceinline__ void store16(const float* e, float sum, uint32_t dst, uint32_t dsw, int c0) {
  const float inv = rcp_fast(sum + __shfl_xor_sync(0xffffffffu, sum, 1));
#pragma unroll
  for (int j = 0; j < 2; j++)
    sts128(dst + (((c0 + j) << 4) ^ dsw), pack_bf16(e[j * 8] * inv, e[j * 8 + 1] * inv), pack_bf16(e[j * 8 + 2] * inv, e[j * 8 + 3] * inv),
           pack_bf16(e[j * 8 + 4] * inv, e[j * 8 + 5] * inv), pack_bf16(e[j * 8 + 6] * inv, e[j * 8 + 7] * inv));
}
__device__ __forceinline__ void expp16(uint32_t* o, const float* p, float c, float b) {
#pragma unroll
  for (int j = 0; j < 8; j++) o[j] = pack_bf16(ex2(fmaf(p[4 * j], c, b)), ex2(fmaf(p[4 * j + 1], c, b)));
}
#define SCHED_FENCE() asm volatile("pmevent 0;" ::: "memory")

__global__ void __cluster_dims__(2, 1, 1) __launch_bounds__(384, 1)
mega_kernel(const __grid_constant__ CUtensorMap tm_x0, const __grid_constant__ CUtensorMap tm_xo,
            const __grid_constant__ CUtensorMap tm_o, const __grid_constant__ CUtensorMap tm_wf,
            const __grid_constant__ CUtensorMap tm_wqA, const __grid_constant__ CUtensorMap tm_wqB,
            const __grid_constant__ CUtensorMap tm_woA, const __grid_constant__ CUtensorMap tm_woB,
            const __grid_constant__ CUtensorMap tm_phi, const Params prm) {
  extern __shared__ __align__(1024) uint8_t smem_raw[];
  const uint32_t sbase = smem_u32(smem_raw);
  const uint32_t bar_full = sbase + OFF_BAR;
  const uint32_t bar_done = bar_full + 384;
  const uint32_t bar_stat = bar_full + 768, bar_stat2 = bar_full + 776, bar_epi = bar_full + 784, bar_phi = bar_full + 792;
  const uint32_t bar_xr = bar_full + 800, bar_lx = bar_full + 808, bar_kvf = bar_full + 816  , bar_stg = bar_full + 832, bar_o1s = bar_full + 840;

  const int warp = __shfl_sync(0xffffffffu, threadIdx.x >> 5, 0), lane = threadIdx.x & 31;
  uint32_t rank;
  asm volatile("mov.u32 %0, %%cluster_ctarank;" : "=r"(rank));
  const int cta = (int)blockIdx.x - NAUX;
  const int cl = cta >> 1;
  const int jj = cl & 7, cc = cl >> 3;
  const int mm = cc * 2 + (int)rank;

  unsigned epoch;
  asm volatile("ld.relaxed.gpu.global.u32 %0, [%1];" : "=r"(epoch) : "l"(&g_flags.epoch.v) : "memory");
  const unsigned ep1 = epoch + 1;

  if (cta >= 0) {
    {
      const int tx = threadIdx.x;
      const __nv_bfloat16* pf = (tx < 128) ? prm.x0 + (size_t)(mm * 128 + tx) * D_MODEL + jj * 128
                                           : prm.wA_qkv + (size_t)(jj * 128 + (tx & 63)) * 3072 + ((tx - 128) >> 6) * 1024 + jj * 128 + rank * 64;
      if (tx < 320) asm volatile("prefetch.global.L2 [%0];" :: "l"(pf));
      else if (tx == 320) prefetch_tmap(&tm_x0);
      else if (tx == 352) prefetch_tmap(&tm_wqA);
    }
    if (threadIdx.x < 48) {
      if (threadIdx.x == 0) {
        mbar_init(bar_stat, 2); mbar_init(bar_stat2, 1); mbar_init(bar_epi, 8); mbar_init(bar_phi, 1);
        mbar_init(bar_xr, 1); mbar_init(bar_lx, 8); mbar_init(bar_kvf, 1); mbar_init(bar_kvf + 8, 1); mbar_init(bar_stg, 8); mbar_init(bar_o1s, 2);
      }
      mbar_init(bar_full + threadIdx.x * 8, 1); mbar_init(bar_done + threadIdx.x * 8, 16);
      asm volatile("fence.mbarrier_init.release.cluster;" ::: "memory");
    }
    __syncthreads();
    asm volatile("barrier.cluster.arrive.relaxed.aligned;" ::: "memory");
  }

  if (cta < 0) {
    const uint32_t buf = sbase + warp * SLOT, bar = sbase + OFF_BAR + warp * 16;
    const uint32_t lsw = (lane & 7) << 4, lhi = (lane >> 4) << 4, lrow = (lane & 15) * 128;
    const bool el = elect_one();
    if (el) {
      mbar_init(bar, 1); mbar_init(bar + 8, 1);
      asm volatile("fence.mbarrier_init.release.cluster;" ::: "memory");
    }
#pragma unroll 1
    for (int rd = 0; rd < (NLAYERS > 1 ? 5 : 2); rd++) {
      if (rd >= 2 && warp >= 8) break;
      const int tk = rd < 2 ? blockIdx.x * 12 + warp : blockIdx.x * 8 + warp;
      const int half = tk & 1;
      const int blk = rd < 2 ? (tk >> 1) * 2 + rd : (rd == 2 ? 32 + (tk >> 1) : (tk >> 1) * 2 + rd - 3);
      const CUtensorMap* tm = rd < 2 ? &tm_wqA : (rd == 2 ? &tm_wqB : &tm_wf);
      const int j0 = (blk & 15) >> 1;
#define AUX_LOAD(n) { const uint32_t d_ = buf + ((n) & 1) * 8192, b_ = bar + ((n) & 1) * 8; const int r_ = kslice(j0, 2 * (n) + half) * 64; \
        mbar_expect_tx(b_, 8192); tma_load_2d(d_, tm, b_, blk * 64, r_); tma_load_2d(d_ + 4096, tm, b_, blk * 64, r_ + 32); }
      if (el) {
        if (rd == 3) { wait_flag(&g_flags.wfready[j0].v, ep1 * 16); fence_proxy_async_global(); }
        AUX_LOAD(0); AUX_LOAD(1);
      }
      __syncwarp();
      float cs[8][4];
#pragma unroll
      for (int i = 0; i < 8; i++) cs[i][0] = cs[i][1] = cs[i][2] = cs[i][3] = 0.f;
#pragma unroll 1
      for (int n = 0; n < 8; n++) {
        const uint32_t tb = buf + (n & 1) * 8192 + lrow;
        mbar_wait(bar + (n & 1) * 8, (n >> 1) & 1);
#pragma unroll
        for (int i = 0; i < 16; i++) {
          uint32_t b0, b1, b2, b3;
          ldsm_x4_t(tb + (i >> 2) * 2048 + (((i & 3) * 32 + lhi) ^ lsw), b0, b1, b2, b3);
          mma_bf16(cs[2 * (i & 3)], 0x3F803F80u, 0x3F803F80u, 0x3F803F80u, 0x3F803F80u, b0, b1);
          mma_bf16(cs[2 * (i & 3) + 1], 0x3F803F80u, 0x3F803F80u, 0x3F803F80u, 0x3F803F80u, b2, b3);
        }
        __syncwarp();
        if (el && n < 6) AUX_LOAD(n + 2);
      }
      if (lane < 4) {
#pragma unroll
        for (int i = 0; i < 8; i++) st_ll(g_colsum[rd >= 2][half] + blk * 32 + i * 4 + lane, __float_as_uint(cs[i][0]), __float_as_uint(cs[i][1]), ep1);
      }
      __syncwarp();
    }
  } else if (warp >= 8) {
    asm volatile("setmaxnreg.dec.sync.aligned.u32 40;");
    if (warp == 8) {
      const bool el = elect_one();
      cluster_wait();
      if (el) {
#pragma unroll 1
        for (int l = 0; l < NLAYERS; l++) {
          const uint32_t par = l & 1;
          const CUtensorMap* tqk = par ? &tm_wf : &tm_wqA;
          const CUtensorMap* tv = par ? &tm_wqB : &tm_wqA;
          const CUtensorMap* two = par ? &tm_woB : &tm_woA;
          if (l == 1) { wait_flag(&g_flags.wfready[jj].v, ep1 * 16); fence_proxy_async_global(); }
#pragma unroll 1
          for (int u = 0; u < 32; u++) {
            if (u >= 4) mbar_wait_sl(bar_done + (u - 4) * 8, par);
            else if (l) mbar_wait_sl(bar_done + (43 + u + (u >> 1)) * 8, par ^ 1);
            else if (u == 1) __nanosleep(STAG1);
            else if (u == 2) mbar_wait_sl(bar_full, 0);
            const uint32_t fb = bar_full + u * 8;
            const bool res = u < 4 ? (l || u >= 2) : (u >= 18 && u < 22);
            mbar_expect_tx(fb, res ? QST : QST + SLOT);
            const int row = kslice(jj, u < 4 ? u & 1 : (u < 18 ? u - 2 : (u < 22 ? u - 6 : u - 20))) * 64 + (int)rank * 32;
            const int col = jj * 128 + (u < 4 ? u >> 1 : (u >= 18)) * 64;
            const uint32_t dst = sbase + (u & 3) * QST + rank * 4096;
            tma_load_2d_mc(dst, tqk, fb, col, row);
            tma_load_2d_mc(dst + 8192, tqk, fb, col + 1024, row);
            tma_load_2d_mc(dst + 16384, tv, fb, col + 2048, row);
          }
#pragma unroll 1
          for (int s = 0; s < 16; s++) {
            if (s < 5) { if (s != 2 && s != 4) mbar_wait_sl(bar_done + (28 + s) * 8, par); }
            else if (s != 14) mbar_wait_sl(bar_done + (27 + s - (s == 15)) * 8, par);
            if (s == 13) mbar_wait_sl(bar_o1s, par);
            const uint32_t fb = bar_full + (32 + s) * 8;
            mbar_expect_tx(fb, (s & 7) ? 2 * SLOT : SLOT);
            tma_load_2d_mc(sbase + rank * 8192 + (uint32_t)((WO_BSLOT >> (4 * s)) & 15) * SLOT, two, fb, jj * 128 + (int)rank * 64, wslice(jj, s) * 64);
          }
        }
      }
      __syncwarp();
    } else if (warp == 9) {
      const bool el = elect_one();
      if (el) {
        tma_load_2d(sbase + OFF_S, &tm_x0, bar_full, jj * 128, mm * 128);
        __nanosleep(STAG1);
        tma_load_2d(sbase + OFF_S + SLOT, &tm_x0, bar_full + 8, jj * 128 + 64, mm * 128);
        mbar_wait_sl(bar_full, 0);
#pragma unroll 1
        for (int l = 0; l < NLAYERS; l++) {
          const uint32_t par = l & 1;
          const CUtensorMap* tx = l ? &tm_xo : &tm_x0;
          if (l) {
            mbar_wait_sl(bar_done + 47 * 8, par ^ 1);
            wait_flag_fast(&g_flags.xready[l][mm][0].v, ep1 * 8);
            fence_proxy_async_global();
            PROFT(320 + l * 16);
          }
#pragma unroll 1
          for (int u = 4; u < 34; u++) {
            if (u == 18) u = 22;
            if (u >= 8) mbar_wait_sl(bar_done + (u - 4) * 8, par);
            if (u == 11 && l) { wait_flag(&g_flags.xready[l][mm][1].v, ep1 * 8); fence_proxy_async_global(); }
            if (u == 32) mbar_expect_tx(bar_xr, 2 * SLOT);
            tma_load_2d(sbase + OFF_RA + (u & 3) * SLOT, tx, u < 32 ? bar_full + u * 8 : bar_xr, kslice(jj, u < 18 ? u - 2 : (u < 32 ? u - 20 : u - 32)) * 64, mm * 128);
            if (l == 0 && u == 7 && NLAYERS > 1) { mbar_expect_tx(bar_phi, 8192); tma_load_2d(sbase + 12 * SLOT, &tm_phi, bar_phi, 0, jj * 128); }
            if (l == 0 && u >= 8 && u < 16) prefetch_l2((const char*)prm.wB_qkv + (size_t)cta * 49152 + (u - 8) * 6144, 6144);
            if (l < 2 && u >= 22 && u < 26) prefetch_l2((const char*)(l ? prm.wB_o : prm.wA_o) + (size_t)cta * 16384 + (u - 22) * 4096, 4096);
          }
          wait_flag_fast(&g_flags.oready[l][mm][0].v, ep1 * 8);
          fence_proxy_async_global();
          PROFT(321 + l * 16);
#pragma unroll 1
          for (int s = 1; s < 16; s++) {
            if (s == 8) {
              mbar_wait_sl(bar_epi, par);
              wait_flag_fast(&g_flags.oready[l][mm][1].v, ep1 * 8);
              fence_proxy_async_global();
              PROFT(322 + l * 16);
              continue;
            }
            if (s == 2 && par) mbar_wait_sl(bar_epi, par);
            if (s < 3) mbar_wait_sl(bar_done + (29 + s) * 8, par);
            else if (s == 3) mbar_wait_sl(bar_lx, par);
            else if (s >= 5 && s < 8) mbar_wait_sl(bar_done + (27 + s) * 8, par);
            else if (s >= 11) mbar_wait_sl(bar_done + (24 + s) * 8, par);
            tma_load_2d(sbase + (uint32_t)((WO_ASLOT >> (4 * s)) & 15) * SLOT, &tm_o, bar_full + (32 + s) * 8, wslice(jj, s) * 64, mm * 128);
          }
        }
      }
      __syncwarp();
      cluster_wait();
    } else {
      const int hw = warp - 10;
      const bool el = elect_one();
      cluster_wait();
      if (hw) {
#pragma unroll 1
        for (int b = 0; b < 2; b++) {
          float4* z = reinterpret_cast<float4*>(g_kv[b] + (jj * 4) * KVH + mm * (4 * KVH / 16)) + lane;
#pragma unroll
          for (int i = 0; i < 5; i++) z[i * 32] = make_float4(0.f, 0.f, 0.f, 0.f);
        }
      }
#pragma unroll 1
      for (int l = 0; l < NLAYERS; l++) {
        {
          mbar_wait_sl(bar_done + 32, l & 1);
          const uint4* sp = reinterpret_cast<const uint4*>(g_stats + (size_t)(mm * 128 + hw * 64) * 8) + lane;
#pragma unroll 1
          for (int hf = 0; hf < 2; hf++) {
            uint4 v[4];
            uint32_t bad;
            int it = 0;
            do {
              bad = 0;
#pragma unroll
              for (int i = 0; i < 4; i++) { v[i] = ld_ll(sp + (hf * 4 + i) * 32); bad |= (v[i].y ^ STAT_TAG(l)) | (v[i].w ^ STAT_TAG(l)); }
              bad &= 3;
              if (bad) __nanosleep(200);
            } while (bad && ++it < (1 << 16));
            __syncwarp();
            float mean = 0.f, m2 = 0.f;
#pragma unroll
            for (int i = 0; i < 4; i++) {
              float a = __uint_as_float(v[i].x) + __uint_as_float(v[i].z);
              a += __shfl_xor_sync(0xffffffffu, a, 1); a += __shfl_xor_sync(0xffffffffu, a, 2);
              a *= 0.125f;
              const float e0 = __uint_as_float(v[i].x) - a, e1 = __uint_as_float(v[i].z) - a;
              float q = fmaf(fmaf(e0, e0, e1 * e1), 128.f, __uint_as_float(v[i].y) + __uint_as_float(v[i].w));
              q += __shfl_xor_sync(0xffffffffu, q, 1); q += __shfl_xor_sync(0xffffffffu, q, 2);
              if ((lane & 3) == i) { mean = a; m2 = q; }
            }
            const uint32_t row = hw * 64 + hf * 32 + (lane & 3) * 8 + (lane >> 2);
            uint32_t h, m, lo;
            split3(-0.5f * mean, h, m, lo);
            sts128(sbase + OFF_LNA + row * 16, h | (h << 16), m | (h << 16), lo | (m << 16), m | (lo << 16));
            sts32f(sbase + OFF_ST + row * 4, rsqrtf(m2 * (1.f / 1024.f) + 1e-5f));
          }
          fence_proxy_async_smem();
          __syncwarp();
          if (el && hw) mbar_arrive_local(bar_stat);
          const uint4* src = g_colsum[l & 1][0] + jj * 64 + hw * 32 + lane;
          uint32_t bad;
          int it = 0;
          float c[6];
          do {
            bad = 0;
#pragma unroll
            for (int p = 0; p < 3; p++) {
              const uint4 v = ld_ll(src + p * 512), w = ld_ll(src + 1536 + p * 512);
              bad |= (v.y ^ ep1) | (v.w ^ ep1) | (w.y ^ ep1) | (w.w ^ ep1);
              c[2 * p] = __uint_as_float(v.x) + __uint_as_float(w.x); c[2 * p + 1] = __uint_as_float(v.z) + __uint_as_float(w.z);
            }
            if (bad) __nanosleep(300);
          } while (bad && ++it < (1 << 16));
#pragma unroll
          for (int p = 0; p < 6; p++) {
            uint32_t h, m, lo;
            split3(c[p], h, m, lo);
            sts128(sbase + OFF_LNB + hw * 3072 + (p >> 1) * 1024 + lane * 32 + (p & 1) * 16, h | (m << 16), h | (lo << 16), h | (m << 16), lo | (m << 16));
          }
          fence_proxy_async_smem();
          __syncwarp();
          if (el) { mbar_arrive_local(hw ? bar_stat2 : bar_stat); PROFT(323 + l * 16 + hw); }
        }
        if (hw) {
          if (l & 1) {
#pragma unroll 1
            for (int h = 0; h < 2; h++) {
              asm volatile("bar.sync %0, 288;" :: "r"(BAR_KV + h) : "memory");
              if (el) {
                PROFT(331 + l * 16 + h);
                signal_release(&g_flags.kvready[l >> 1][jj][h].v);
                wait_flag_fast(&g_flags.kvready[l >> 1][jj][h].v, ep1 * 16);
                mbar_arrive_local(bar_kvf + h * 8);
                PROFT(333 + l * 16 + h);
              }
              __syncwarp();
            }
          } else if (l == 0 && NLAYERS > 1) {
            bar_sync<BAR_WF, 288>();
            if (el) { signal_release(&g_flags.wfready[jj].v); PROFT(335); }
            __syncwarp();
          }
        }
#pragma unroll 1
        for (int e = hw * 3; e < 3 + hw; e++) {
          asm volatile("bar.sync %0, 288;" :: "r"(BAR_O + e) : "memory");
          if (el) {
            PROFT(325 + l * 16 + e);
            tma_store_2d((e & 2) ? &tm_xo : &tm_o, sbase + ((0xBA3C >> (4 * e)) & 15) * SLOT, jj * 128 + (e & 1) * 64, mm * 128);
            bulk_commit_wait();
            if (e == 1) { mbar_arrive_remote(bar_o1s, 0); mbar_arrive_remote(bar_o1s, 1); }
            if (e == 1 || e == 2) PROFT(480 + l * 2 + e - 1);
            if (e < 2) signal_release(&g_flags.oready[l][mm][e].v);
            else if (l < NLAYERS - 1) signal_release(&g_flags.xready[l + 1][mm][e & 1].v);
            if (e == 1 || e == 2) PROFT(328 + l * 16 + e);
          }
          __syncwarp();
        }
      }
    }
    cluster_sync();
  } else {
    asm volatile("setmaxnreg.inc.sync.aligned.u32 232;");
    const int wg = warp >> 2;
    const int r0 = warp * 16;
    const uint32_t pK = sbase + OFF_S, pV = sbase + OFF_S + SLOT;
#define LANE_CONSTS() \
    int lane; asm volatile("mov.u32 %0, %%laneid;" : "=r"(lane)); \
    const int g = lane >> 2, t = lane & 3; \
    const uint32_t srowoff = (r0 + (lane & 15)) * 128, lsw = (lane & 7) << 4, lhi = (lane >> 4) << 4, lsw2 = (lane & 6) << 3; \
    (void)g; (void)t; (void)srowoff; (void)lsw; (void)lhi; (void)lsw2;
    uint32_t stgp = 0;
    if (warp < 2) sts128(sbase + OFF_ONES + threadIdx.x * 16, 0x3F803F80u, 0x3F803F80u, 0x3F803F80u, 0x3F803F80u);
    cluster_wait();
#define STG_ARRIVE() { __syncwarp(); if (elect_one()) mbar_arrive_local(bar_stg); }
#define STG_WAIT() { mbar_wait(bar_stg, stgp); stgp ^= 1; }
#define PROFS() do {} while (0)
#define REL(addr) { if (elect_one()) { mbar_arrive_remote(addr, 0); mbar_arrive_remote(addr, 1); } }
#define QSTEP(ACC, AADDR, SC, PRE) { \
      const uint64_t da = make_desc(AADDR, 16, 1024), db = make_desc(sbase + ((ub >> 3) & 3) * QST, 8192, 1024); \
      mbar_wait(ub, par); \
      PRE; \
      wgmma_fence(); \
      wgmma_n192<SC>(ACC, da, db); \
      _Pragma("unroll") for (int k4 = 1; k4 < 4; k4++) wgmma_n192<1>(ACC, da + k4 * 2, db + k4 * 128); \
      wgmma_commit(); PROFS(); }
#define QREL() { wgmma_wait<1>(); REL(ub + 376); ub += 8; }
#define RA_CUR (sbase + OFF_RA + ((ub << 11) & 0xC000) + wg * 8192)
#define PUMP0() { QSTEP(S1, RA_CUR, 1, {}); QREL(); SCHED_FENCE(); }
#define PUMP() if (h == 0) PUMP0()
#define PUMPC() { if (h == 0) PUMP0() else wgmma_wait<0>(); }
#define WSTEP() { \
      const uint32_t s4 = (ub - bar_full - 256) >> 1; \
      const uint64_t da = make_desc(sbase + (uint32_t)((WO_ASLOT >> s4) & 15) * SLOT + wg * 8192, 16, 1024); \
      const uint64_t db = make_desc(sbase + (uint32_t)((WO_BSLOT >> s4) & 15) * SLOT, 8192, 1024); \
      mbar_wait(ub, par); \
      wgmma_fence(); \
      _Pragma("unroll") for (int k4 = 0; k4 < 4; k4++) wgmma_n128<1>(S1, da + k4 * 2, db + k4 * 128); \
      wgmma_commit(); PROFS(); \
      wgmma_wait<1>(); \
      if (s4) REL(ub + 376); \
      ub += 8; }
#define PUMPS(n) { _Pragma("unroll 1") for (int i_ = 0; i_ < (n); i_++) PUMP0(); }
#define SITE(n) { if (((BMASK >> (n)) & 1) && h == 0) PUMP0() else SCHED_FENCE(); }
#define LNSTEP(ACC, hh) { wgmma_fence(); wgmma_n192<1, 0>(ACC, make_desc(sbase + OFF_LNA + wg * 1024, 0, 128) ^ (1ull << 62), make_desc(sbase + OFF_LNB + (hh) * 3072, 0, 128) ^ (1ull << 62)); }
#define DRAIN_A(ACC, PMP) { \
      LANE_CONSTS(); \
      STAGE64(ACC, 64, pV, 1); \
      PMP; \
      STAGE64(ACC, 32, pK, 0); \
      STG_ARRIVE(); \
      _Pragma("unroll") for (int i_ = 0; i_ < 16; i_++) qa[i_] = pack_bf16(ACC[2 * i_], ACC[2 * i_ + 1]); \
      PINU(qa, 16); }
#define DRAIN_B(ACC) { \
      LANE_CONSTS(); \
      STAGE64(ACC, 64, pV, 1); \
      _Pragma("unroll") for (int i_ = 0; i_ < 64; i_++) st[i_] = ACC[i_]; \
      PIN(st, 64); }
#define PUBLISH_O() { fence_proxy_async_smem(); asm volatile("bar.arrive %0, 288;" :: "r"(BAR_O + h) : "memory"); }
#define REST_P1(SKEW) { \
      mbar_wait(bar_stat2, par); \
      LNSTEP(S1, 1); \
      _Pragma("unroll 1") while (ub < bar_full + 256) { \
        if (ub == bar_full + 256 - 8 * (SKEW) && wg == 0) bar_sync<BAR_SKEW, 256>(); \
        QSTEP(S1, RA_CUR, 1, {}); \
        if (ub == bar_full + 248 && wg == 1) bar_arrive<BAR_SKEW, 256>(); \
        QREL(); \
      } \
      hbase += 256; \
      mbar_wait(bar_done + (31 - (SKEW)) * 8, par);        \
      wgmma_wait<0>(); \
      ACC_FENCE(S1, 96); \
      REL(bar_done + 31 * 8); \
      PROF(13); }
#define LOAD_X0(base) \
      _Pragma("unroll") for (int j = 0; j < 8; j++) { \
        uint32_t x0, x1, x2, x3; \
        ldsm_x4((base) + (j >> 2) * SLOT + srowoff + ((((uint32_t)(j & 3) << 5) + lhi) ^ lsw), x0, x1, x2, x3); \
        S1[j * 8 + 0] = bf_lo(x0); S1[j * 8 + 1] = bf_hi(x0); S1[j * 8 + 2] = bf_lo(x1); S1[j * 8 + 3] = bf_hi(x1); \
        S1[j * 8 + 4] = bf_lo(x2); S1[j * 8 + 5] = bf_hi(x2); S1[j * 8 + 6] = bf_lo(x3); S1[j * 8 + 7] = bf_hi(x3); \
      }
#define LOAD_X() { \
      wgmma_wait<0>(); \
      mbar_wait(bar_xr, par); \
      LOAD_X0(sbase + OFF_RA); \
      ACC_FENCE(S1, 64); \
      __syncwarp(); if (elect_one()) mbar_arrive_local(bar_lx); }

    float S1[96];
#pragma unroll
    for (int i = 0; i < 64; i++) S1[i] = 0.f;
#pragma unroll 1
    for (int l = 0; l < NLAYERS; l++) {
      const uint32_t par = l & 1;
      bar_wg(wg);
      PROF(0);
      uint32_t ub = bar_full;
      const bool hsend = (warp == 7) && !par && (mm < 15);
      const uint32_t hbit = (NLAYERS > 2) ? (l == 0) : (ep1 & 1);
      float S0[96];
      {
        LANE_CONSTS();
        ACC_DEF(S0, 96);
        QSTEP(S0, pK + wg * 8192, 0, {});
        ub += 8;
        PROF(1);
        if (l == 0) { mbar_wait(ub, 0); LOAD_X0(pK); }
        SCHED_FENCE();
        {
          float a0 = 0.f, a1 = 0.f, b0 = 0.f, b1 = 0.f;
#pragma unroll
          for (int i = 0; i < 64; i += 4) { a0 += S1[i]; b0 += S1[i + 1]; a1 += S1[i + 2]; b1 += S1[i + 3]; }
          a0 += b0; a1 += b1;
          a0 += __shfl_xor_sync(0xffffffffu, a0, 1); a1 += __shfl_xor_sync(0xffffffffu, a1, 1);
          a0 += __shfl_xor_sync(0xffffffffu, a0, 2); a1 += __shfl_xor_sync(0xffffffffu, a1, 2);
          a0 *= (1.f / 128.f); a1 *= (1.f / 128.f);
          asm volatile("" : "+f"(a0), "+f"(a1));
          QSTEP(S0, pV + wg * 8192, 1, wgmma_wait<0>());
          REL(ub + 376); ub += 8;
          SCHED_FENCE();
          float q0 = 0.f, q1 = 0.f;
          b0 = 0.f; b1 = 0.f;
#pragma unroll
          for (int i = 0; i < 64; i += 4) {
            const float d0 = S1[i] - a0, d1 = S1[i + 1] - a0, d2 = S1[i + 2] - a1, d3 = S1[i + 3] - a1;
            q0 = fmaf(d0, d0, q0); b0 = fmaf(d1, d1, b0); q1 = fmaf(d2, d2, q1); b1 = fmaf(d3, d3, b1);
          }
          q0 += b0; q1 += b1;
          q0 += __shfl_xor_sync(0xffffffffu, q0, 1); q1 += __shfl_xor_sync(0xffffffffu, q1, 1);
          q0 += __shfl_xor_sync(0xffffffffu, q0, 2); q1 += __shfl_xor_sync(0xffffffffu, q1, 2);
          if (t < 2) st_b64(g_stats + (size_t)(mm * 128 + r0 + g + t * 8) * 8 + jj, __float_as_uint(t ? a1 : a0), (__float_as_uint(t ? q1 : q0) & ~3u) | STAT_TAG(l));
        }
        ACC_DEF(S1, 96);
        QSTEP(S1, pK + wg * 8192, 0, {});
        QREL();
        QSTEP(S1, pV + wg * 8192, 1, {});
        QREL();
#pragma unroll 1
        for (int i = 0; i < 14; i++) {
          QSTEP(S0, RA_CUR, 1, {});
          if (i == 0) PROF(2);
          QREL();
        }
      }
      LANE_CONSTS();
      uint4* hbase = g_halo + (size_t)(mm * 8 + jj) * 512;
      mbar_wait(bar_stat, par);
      LNSTEP(S0, 0);
      wgmma_commit();
      const float rs0 = lds32f(sbase + OFF_ST + (r0 + g) * 4), rs1 = lds32f(sbase + OFF_ST + (r0 + g + 8) * 4);
      PUMP0();
      ACC_FENCE(S0, 96);
      PROF(3);
      if (!par) {
        uint32_t qa[16];
        DRAIN_A(S0, PUMP0());
#pragma unroll 1
        for (int h = 0; h < 2; h++) {
          const uint32_t pO = sbase + (h ? 3 : 12) * SLOT;
          const bool fold = (l == 0 && h == 0 && NLAYERS > 1);
          PROF(4 + h * 12);
          if (h == 0) PUMPS(HPUMP1);
          if (fold) {
            LANE_CONSTS();
            const size_t wrow = (size_t)(mm * 64 + (warp >> 1) * 16);
            const uint4* src = reinterpret_cast<const uint4*>(prm.wB_qkv + (wrow + g) * 3072 + (warp & 1) * 1024 + jj * 128) + t;
            uint4* dstw = reinterpret_cast<uint4*>(g_wfold + (wrow + 2 * t) * 2048 + (warp & 1) * 1024 + jj * 128) + g;
            uint4 b[8];
#pragma unroll
            for (int i = 0; i < 8; i++) b[i] = __ldg(src + (i & 1) * 3072 + (i >> 1) * 4);
            PUMPS(2);
            mbar_wait(bar_phi, 0);
            const uint32_t pa = pO + (8 * ((lane & 7) >> 1) + (lane & 1) + 2 * (lane >> 4)) * 64;
            uint32_t w[2][2][4];
#pragma unroll
            for (int h4 = 0; h4 < 4; h4++) {
              uint32_t af[2][2][4];
#pragma unroll
              for (int i = 0; i < 4; i++)
                ldsm_x4_t(pa + h4 * 2048 + (i & 1) * 256 + (((i >> 1) * 32 + ((lane >> 3) & 1) * 16) ^ (lhi + (i & 1) * 32)),
                          af[i >> 1][i & 1][0], af[i >> 1][i & 1][1], af[i >> 1][i & 1][2], af[i >> 1][i & 1][3]);
              float c0[2][4], c1[2][4];
#pragma unroll
              for (int i = 0; i < 2; i++) {
                const uint4 bb = b[h4 * 2 + i];
                c0[i][0] = c0[i][1] = c0[i][2] = c0[i][3] = c1[i][0] = c1[i][1] = c1[i][2] = c1[i][3] = 0.f;
                mma_bf16(c0[i], af[0][0][0], af[0][0][1], af[0][0][2], af[0][0][3], bb.x, bb.y);
                mma_bf16(c1[i], af[1][0][0], af[1][0][1], af[1][0][2], af[1][0][3], bb.x, bb.y);
              }
#pragma unroll
              for (int i = 0; i < 2; i++) {
                const uint4 bb = b[h4 * 2 + i];
                mma_bf16(c0[i], af[0][1][0], af[0][1][1], af[0][1][2], af[0][1][3], bb.z, bb.w);
                mma_bf16(c1[i], af[1][1][0], af[1][1][1], af[1][1][2], af[1][1][3], bb.z, bb.w);
              }
#pragma unroll
              for (int i = 0; i < 2; i++) {
                w[i][0][(h4 & 1) * 2] = pack_bf16(c0[i][0], c0[i][2]); w[i][0][(h4 & 1) * 2 + 1] = pack_bf16(c1[i][0], c1[i][2]);
                w[i][1][(h4 & 1) * 2] = pack_bf16(c0[i][1], c0[i][3]); w[i][1][(h4 & 1) * 2 + 1] = pack_bf16(c1[i][1], c1[i][3]);
              }
              if (h4 & 1) {
#pragma unroll
                for (int i = 0; i < 4; i++)
                  dstw[((i >> 1) * 8 + (i & 1)) * 256 + (h4 >> 1) * 8] = make_uint4(w[i >> 1][i & 1][0], w[i >> 1][i & 1][1], w[i >> 1][i & 1][2], w[i >> 1][i & 1][3]);
              }
            }
            fence_proxy_async_global();
            bar_arrive<BAR_WF, 288>();
            PROF(12);
          }
          LANE_CONSTS();
          uint4 hv[8];
#pragma unroll
          for (int i = 0; i < 8; i++) hv[i] = make_uint4(hbit, 0, 0, 0);
          const bool hrec = (warp == 0 && mm > 0);
          if (hrec) {
#pragma unroll
            for (int i = 0; i < 8; i++) hv[i] = ld_b128(hbase + lane - 8 * 512 + i * 32);
          }
          if (h) LOAD_X() else PUMPS(HPUMP2);
          const uint32_t halo = sbase + OFF_HALO;
          if (warp == 0) {
#pragma unroll 1
            for (int it = 0; it < (1 << 16); it++) {
              uint32_t bad = 0;
#pragma unroll
              for (int i = 0; i < 8; i++) bad |= hv[i].x ^ hbit;
              if (__all_sync(0xffffffffu, (bad & 1) == 0)) break;
#pragma unroll
              for (int i = 0; i < 8; i++) hv[i] = ld_b128(hbase + lane - 8 * 512 + i * 32);
            }
#pragma unroll
            for (int i = 0; i < 8; i++)
              stsm_x4(i < 4 ? halo + srowoff + ((((uint32_t)i << 5) + lhi) ^ lsw)
                            : halo + (srowoff >> 1) + (i >> 1) * 1024 + ((((uint32_t)(i & 1) << 5) + lhi) ^ lsw2), hv[i].x, hv[i].y, hv[i].z, hv[i].w);
            __syncwarp();
          }
          STG_WAIT();
          PROF(5 + h * 12);
          const uint32_t kb1 = pK + r0 * 128, vb1 = pV + r0 * 64;
          const uint32_t kb0 = r0 ? kb1 - 2048 : halo, vb0 = r0 ? vb1 - 1024 : halo + 2048;
          const uint32_t vhs = r0 ? 8192 : 1024;
          float s[2][4][4];
          {
            uint32_t kf[2][4][4];
#pragma unroll
            for (int i = 0; i < 8; i++) {
              const int hh = i >> 2, jb = i & 3;
              ldsm_x4(((jb < 2) ? kb0 : kb1) + ((jb & 1) * 8 + (lane & 7)) * 128 + ((hh * 64 + ((lane >> 3) << 4)) ^ lsw), kf[hh][jb][0], kf[hh][jb][1], kf[hh][jb][2], kf[hh][jb][3]);
              s[hh][jb][0] = s[hh][jb][1] = s[hh][jb][2] = s[hh][jb][3] = 0.f;
            }
#pragma unroll
            for (int ks = 0; ks < 2; ks++)
#pragma unroll
              for (int i = 0; i < 8; i++) {
                const int hh = i >> 2, jb = i & 3;
                mma_bf16(s[hh][jb], qa[hh * 8 + ks * 4], qa[hh * 8 + ks * 4 + 1], qa[hh * 8 + ks * 4 + 2], qa[hh * 8 + ks * 4 + 3], kf[hh][jb][ks * 2], kf[hh][jb][ks * 2 + 1]);
              }
          }
          PUMP();
          PROF(6 + h * 12);
          const bool e = g & 1, hb = (2 * t + (g & 1)) <= g;
          uint32_t vf[2][2][2][4];
#pragma unroll
          for (int i = 0; i < 8; i++) {
            const int hh = i >> 2, ks = (i >> 1) & 1, dp = i & 1;
            ldsm_x4_t((ks ? vb1 + hh * 8192 : vb0 + hh * vhs) + (lane & 15) * 64 + ((dp * 32 + lhi) ^ lsw2), vf[hh][ks][dp][0], vf[hh][ks][dp][1], vf[hh][ks][dp][2], vf[hh][ks][dp][3]);
          }
          float va[2][2], vb[2][2], mx[2][2];
#pragma unroll
          for (int hh = 0; hh < 2; hh++) {
            va[hh][0] = e ? s[hh][1][1] : s[hh][1][0];
            vb[hh][0] = hb ? (e ? s[hh][2][1] : s[hh][2][0]) : (e ? s[hh][0][1] : s[hh][0][0]);
            va[hh][1] = e ? s[hh][2][3] : s[hh][2][2];
            vb[hh][1] = hb ? (e ? s[hh][3][3] : s[hh][3][2]) : (e ? s[hh][1][3] : s[hh][1][2]);
          }
          if (warp == 0 && mm == 0) {
#pragma unroll
            for (int hh = 0; hh < 2; hh++) { va[hh][0] = -INFINITY; if (!hb) { vb[hh][0] = -INFINITY; vb[hh][1] = -INFINITY; } }
          }
#pragma unroll
          for (int i = 0; i < 4; i++) mx[i >> 1][i & 1] = fmaxf(va[i >> 1][i & 1], vb[i >> 1][i & 1]);
#pragma unroll
          for (int o = 1; o <= 2; o <<= 1)
#pragma unroll
            for (int i = 0; i < 4; i++) mx[i >> 1][i & 1] = fmaxf(mx[i >> 1][i & 1], __shfl_xor_sync(0xffffffffu, mx[i >> 1][i & 1], o));
          const float sc0 = rs0 * (0.17677669529663687f * LOG2E), sc1 = rs1 * (0.17677669529663687f * LOG2E);
#pragma unroll
          for (int i = 0; i < 4; i++) {
            const float sc = (i & 1) ? sc1 : sc0, m = mx[i >> 1][i & 1];
            va[i >> 1][i & 1] = ex2((va[i >> 1][i & 1] - m) * sc); vb[i >> 1][i & 1] = ex2((vb[i >> 1][i & 1] - m) * sc);
            mx[i >> 1][i & 1] = va[i >> 1][i & 1] + vb[i >> 1][i & 1];
          }
          if (h == 0 && ASITE) { PIN(&va[0][0], 4); PIN(&vb[0][0], 4); PIN(&mx[0][0], 4); PUMP0(); }
#pragma unroll
          for (int o = 1; o <= 2; o <<= 1)
#pragma unroll
            for (int i = 0; i < 4; i++) mx[i >> 1][i & 1] += __shfl_xor_sync(0xffffffffu, mx[i >> 1][i & 1], o);
          const uint32_t selA = e ? 0x1044 : 0x4410, selB = e ? 0x3244 : 0x4432, selL = hb ? 0x4444 : selB, selH = hb ? selB : 0x4444;
          float o[2][4][4];
          uint32_t pa[2][6];
#pragma unroll
          for (int hh = 0; hh < 2; hh++) {
            const float i0 = rcp_fast(mx[hh][0]), i1 = rcp_fast(mx[hh][1]);
            const uint32_t w0 = pack_bf16(va[hh][0] * i0, vb[hh][0] * i0), w1 = pack_bf16(va[hh][1] * i1, vb[hh][1] * i1);
            pa[hh][0] = __byte_perm(w0, 0, selL); pa[hh][1] = __byte_perm(w0, 0, selA); pa[hh][2] = __byte_perm(w1, 0, selL);
            pa[hh][3] = __byte_perm(w0, 0, selH); pa[hh][4] = __byte_perm(w1, 0, selA); pa[hh][5] = __byte_perm(w1, 0, selH);
#pragma unroll
            for (int dj = 0; dj < 4; dj++) { o[hh][dj][0] = o[hh][dj][1] = o[hh][dj][2] = o[hh][dj][3] = 0.f; }
          }
          PROF(7 + h * 12);
#pragma unroll
          for (int i = 0; i < 8; i++) mma_bf16(o[i >> 2][i & 3], pa[i >> 2][0], 0u, pa[i >> 2][1], pa[i >> 2][2], vf[i >> 2][0][(i >> 1) & 1][(i & 1) * 2], vf[i >> 2][0][(i >> 1) & 1][(i & 1) * 2 + 1]);
#pragma unroll
          for (int i = 0; i < 8; i++) mma_bf16(o[i >> 2][i & 3], pa[i >> 2][3], pa[i >> 2][4], 0u, pa[i >> 2][5], vf[i >> 2][1][(i >> 1) & 1][(i & 1) * 2], vf[i >> 2][1][(i >> 1) & 1][(i & 1) * 2 + 1]);
          if (h == 0) PUMP0() else mbar_wait(bar_done + 30 * 8, par);
#pragma unroll
          for (int i = 0; i < 4; i++) {
            const int hh = i >> 1, dp = i & 1;
            stsm_x4(pO + srowoff + ((hh * 64 + dp * 32 + lhi) ^ lsw), pack_bf16(o[hh][dp * 2][0], o[hh][dp * 2][1]), pack_bf16(o[hh][dp * 2][2], o[hh][dp * 2][3]),
                    pack_bf16(o[hh][dp * 2 + 1][0], o[hh][dp * 2 + 1][1]), pack_bf16(o[hh][dp * 2 + 1][2], o[hh][dp * 2 + 1][3]));
          }
          PUBLISH_O();
          PROF(11 + h * 12);
          if (h) break;
          REST_P1(ASKEW);
          DRAIN_A(S1, {});
        }
      } else {
        float st[64];
        DRAIN_B(S0);
        const float c0 = rs0 * LOG2E, c1 = rs1 * LOG2E;
#pragma unroll 1
        for (int h = 0; h < 2; h++) {
          const uint32_t pO = sbase + (h ? 3 : 12) * SLOT, pP = sbase + (h ? 9 : 10) * SLOT;
          PROF(4 + h * 12);
          SITE(0);
          LANE_CONSTS();
          const uint32_t dsw = (uint32_t)(g ^ (2 * t)) << 4;
          const float* pk = st + 32;
          float4* kvg = reinterpret_cast<float4*>(g_kv[l >> 1] + (jj * 4 + h * 2 + wg) * KVH) + (warp & 3) * 32 + lane;
          const uint32_t dst = ((t & 2) ? pP : pO) + (r0 + g) * 128;
          float mq[4];
          {
            float e[16], f[16];
            float mn0 = rmin16(pk);
            asm volatile("" : "+f"(mn0)); SCHED_FENCE();
            float sa = exps16(e, pk, -c0, mn0 * c0), mx0 = rmax16(pk);
            asm volatile("" : "+f"(sa), "+f"(mx0)); PIN(e, 16); SITE(1);
            store16(e, sa, dst, dsw, 4);
            float sb = exps16(f, pk, c0, -mx0 * c0), mn1 = rmin16(pk + 2);
            asm volatile("" : "+f"(sb), "+f"(mn1)); PIN(f, 16); SITE(2);
            store16(f, sb, dst, dsw, 0);
            float sc = exps16(e, pk + 2, -c1, mn1 * c1), mx1 = rmax16(pk + 2);
            asm volatile("" : "+f"(sc), "+f"(mx1)); PIN(e, 16); SITE(3);
            store16(e, sc, dst + 1024, dsw, 4);
            float sd = exps16(f, pk + 2, c1, -mx1 * c1);
            asm volatile("" : "+f"(sd)); PIN(f, 16); SITE(4);
            store16(f, sd, dst + 1024, dsw, 0);
          }
          fence_proxy_async_smem();
          STG_ARRIVE();
          PROF(5 + h * 12);
          uint32_t fq[32];
          {
            float kv[20];
            ACC_DEF(kv, 20);
            const uint64_t dp = make_desc(wg ? pP : pO, 16, 1024);
            const uint64_t dv = (make_desc(pV + wg * 8192, OFF_ONES - OFF_S - SLOT - wg * 8192, 512) ^ (3ull << 62));
            constexpr uint64_t DVS = 64ull - (64ull << 16);
            mq[0] = rmin16(st);
            asm volatile("" : "+f"(mq[0])); SITE(5);
            STG_WAIT();
            wgmma_fence();
#pragma unroll
            for (int ks = 0; ks < 8; ks++) { if (ks == 0) wgmma_n40<0, 1>(kv, dp, dv); else wgmma_n40<1, 1>(kv, dp + ks * 128, dv + ks * DVS); }
            wgmma_commit();
            SCHED_FENCE();
            mq[1] = rmax16(st); mq[2] = rmin16(st + 2); mq[3] = rmax16(st + 2);
            asm volatile("" : "+f"(mq[1]), "+f"(mq[2]), "+f"(mq[3]));
            PUMPC();
            ACC_FENCE(kv, 20);
#pragma unroll
            for (int i = 0; i < 5; i++) red_v4(reinterpret_cast<float*>(kvg + i * 128), kv[i * 4], kv[i * 4 + 1], kv[i * 4 + 2], kv[i * 4 + 3]);
            asm volatile("bar.arrive %0, 288;" :: "r"(BAR_KV + h) : "memory");
            STG_ARRIVE();
          }
          PROF(6 + h * 12);
          expp16(fq, st, -c0, mq[0] * c0);
          PINU(fq, 8); SITE(6);
          expp16(fq + 8, st, c0, -mq[1] * c0);
          PINU(fq + 8, 8); SITE(7);
          STG_WAIT();
#pragma unroll
          for (int i = 0; i < 4; i++) sts128(dst + (((((i & 2) ? 0 : 4) + (i & 1)) << 4) ^ dsw), fq[i * 4], fq[i * 4 + 1], fq[i * 4 + 2], fq[i * 4 + 3]);
          expp16(fq + 16, st + 2, -c1, mq[2] * c1);
          PINU(fq + 16, 8); SITE(8);
          expp16(fq + 24, st + 2, c1, -mq[3] * c1);
#pragma unroll
          for (int i = 4; i < 8; i++) sts128(dst + 1024 + (((((i & 2) ? 0 : 4) + (i & 1)) << 4) ^ dsw), fq[i * 4], fq[i * 4 + 1], fq[i * 4 + 2], fq[i * 4 + 3]);
          PROF(7 + h * 12);
          if (h) break;
          REST_P1(1);
          DRAIN_B(S1);
        }
#pragma unroll 1
        for (int h = 0; h < 2; h++) {
          const uint32_t pO = sbase + (h ? 3 : 12) * SLOT, pP = sbase + (h ? 9 : 10) * SLOT;
          LANE_CONSTS();
          {
            const float4* kvg = reinterpret_cast<const float4*>(g_kv[l >> 1] + (jj * 4 + h * 2 + wg) * KVH) + (warp & 3) * 32 + lane;
            mbar_wait(bar_kvf + h * 8, l >> 1);
            PROF(24 + h * 8);
            float4 v[5];
#pragma unroll
            for (int i = 0; i < 5; i++) v[i] = __ldcg(kvg + i * 128);
            if (h) STG_WAIT() else LOAD_X();
            const uint32_t kd = pV + wg * 8192 + ((warp & 3) * 16 + (lane & 15)) * 128;
#pragma unroll
            for (int i = 0; i < 2; i++) {
              const float4 a = v[i * 2], b = v[i * 2 + 1];
              stsm_x4(kd + ((i * 32 + lhi) ^ lsw), pack_bf16(a.x, a.y), pack_bf16(a.z, a.w), pack_bf16(b.x, b.y), pack_bf16(b.z, b.w));
            }
            stsm_x4(kd + ((64u + lhi) ^ lsw), pack_bf16(v[4].x, 1.f), pack_bf16(v[4].z, 1.f), 0u, 0u);
          }
          fence_proxy_async_smem();
          STG_ARRIVE();
          float o[4][20];
          ACC_DEF(o[0], 20); ACC_DEF(o[1], 20); ACC_DEF(o[2], 20); ACC_DEF(o[3], 20);
          STG_WAIT();
          PROF(25 + h * 8);
          wgmma_fence();
#pragma unroll
          for (int hh = 0; hh < 2; hh++) {
            const uint64_t da = make_desc((hh ? pP : pO) + wg * 8192, 16, 1024);
            const uint64_t db = make_desc(pV + hh * 8192, 16, 1024);
#pragma unroll
            for (int ks = 0; ks < 4; ks += 2) { wgmma_n40<0, 0>(o[hh * 2 + (ks >> 1)], da + ks * 2, db + ks * 128); wgmma_n40<1, 0>(o[hh * 2 + (ks >> 1)], da + ks * 2 + 2, db + ks * 128 + 128); }
          }
          wgmma_commit();
          wgmma_wait<0>();
          ACC_FENCE(o[0], 20); ACC_FENCE(o[1], 20); ACC_FENCE(o[2], 20); ACC_FENCE(o[3], 20);
          if (h == 0) STG_ARRIVE();
          bar_wg(wg);
#pragma unroll
          for (int hh = 0; hh < 2; hh++) {
            const float* x = o[hh * 2];
            const float* y = o[hh * 2 + 1];
            const float rx0 = rcp_fast(x[17]), ry0 = rcp_fast(y[17]), rx1 = rcp_fast(x[19]), ry1 = rcp_fast(y[19]);
            const float i0 = rcp_fast(fmaf(x[16], rx0, y[16] * ry0) + 1e-6f), i1 = rcp_fast(fmaf(x[18], rx1, y[18] * ry1) + 1e-6f);
            const float ax0 = rx0 * i0, ay0 = ry0 * i0, ax1 = rx1 * i1, ay1 = ry1 * i1;
#pragma unroll
            for (int dp = 0; dp < 2; dp++)
              stsm_x4(pO + srowoff + ((hh * 64 + dp * 32 + lhi) ^ lsw),
                      pack_bf16(fmaf(x[dp * 8], ax0, y[dp * 8] * ay0), fmaf(x[dp * 8 + 1], ax0, y[dp * 8 + 1] * ay0)),
                      pack_bf16(fmaf(x[dp * 8 + 2], ax1, y[dp * 8 + 2] * ay1), fmaf(x[dp * 8 + 3], ax1, y[dp * 8 + 3] * ay1)),
                      pack_bf16(fmaf(x[dp * 8 + 4], ax0, y[dp * 8 + 4] * ay0), fmaf(x[dp * 8 + 5], ax0, y[dp * 8 + 5] * ay0)),
                      pack_bf16(fmaf(x[dp * 8 + 6], ax1, y[dp * 8 + 6] * ay1), fmaf(x[dp * 8 + 7], ax1, y[dp * 8 + 7] * ay1)));
          }
          PUBLISH_O();
          PROF(26 + h * 8);
          if (h) break;
          bar_wg(wg);
          WSTEP();
        }
      }
      __syncwarp();
      if (elect_one()) mbar_arrive_local(bar_epi);
      bar_wg(wg);
#pragma unroll 1
      while (ub < bar_full + 384) {
        WSTEP();
        if (ub == bar_full + 8 * 41) PROF(35);
        if (ub == bar_full + 8 * 42) PROF(36);
      }
      wgmma_wait<0>();
      ACC_FENCE(S1, 64);
      REL(bar_done + 47 * 8);
      PROF(37);
      {
      LANE_CONSTS();
#pragma unroll
      for (int j = 0; j < 8; j++) {
        stsm_x4(pK + (j >> 2) * SLOT + srowoff + ((((uint32_t)(j & 3) << 5) + lhi) ^ lsw),
                pack_bf16(S1[j * 8 + 0], S1[j * 8 + 1]), pack_bf16(S1[j * 8 + 2], S1[j * 8 + 3]),
                pack_bf16(S1[j * 8 + 4], S1[j * 8 + 5]), pack_bf16(S1[j * 8 + 6], S1[j * 8 + 7]));
        if (j == 3) { fence_proxy_async_smem(); bar_arrive<BAR_O + 2, 288>(); }
      }
      }
      fence_proxy_async_smem();
      bar_arrive<BAR_O + 3, 288>();
      PROF(38);
    }
    const int tid = threadIdx.x;
    if (tid == 0) {
      unsigned old = atomicAdd(&g_flags.done.v, 1);
      if (old == ep1 * NMAIN - 1) {
        asm volatile("st.relaxed.gpu.global.u32 [%0], %1;" :: "l"(&g_flags.epoch.v), "r"(ep1) : "memory");
      }
    }
    __syncwarp();
    cluster_sync();
  }
}

typedef CUresult (*PFN_encode)(CUtensorMap*, CUtensorMapDataType, cuuint32_t, void*, const cuuint64_t*, const cuuint64_t*,
                               const cuuint32_t*, const cuuint32_t*, CUtensorMapInterleave, CUtensorMapSwizzle,
                               CUtensorMapL2promotion, CUtensorMapFloatOOBfill);

CUtensorMap make_map(PFN_encode enc, const void* ptr, uint64_t inner, uint64_t outer, uint32_t box_inner, uint32_t box_outer,
                     CUtensorMapSwizzle swz = CU_TENSOR_MAP_SWIZZLE_128B) {
  CUtensorMap m;
  cuuint64_t dims[2] = {inner, outer};
  cuuint64_t strides[1] = {inner * 2};
  cuuint32_t box[2] = {box_inner, box_outer};
  cuuint32_t es[2] = {1, 1};
  enc(&m, CU_TENSOR_MAP_DATA_TYPE_BFLOAT16, 2, const_cast<void*>(ptr), dims, strides, box, es, CU_TENSOR_MAP_INTERLEAVE_NONE,
      swz, CU_TENSOR_MAP_L2_PROMOTION_L2_256B, CU_TENSOR_MAP_FLOAT_OOB_FILL_NONE);
  return m;
}

}

extern "C" void kernel_launch(void* const* d_in, const int* in_sizes, int n_in, void* d_out, int out_size) {
  (void)in_sizes; (void)n_in; (void)out_size;
  static PFN_encode enc = nullptr;
  if (!enc) {
    void* fn = nullptr;
    cudaDriverEntryPointQueryResult qr;
    cudaGetDriverEntryPoint("cuTensorMapEncodeTiled", &fn, cudaEnableDefault, &qr);
    enc = (PFN_encode)fn;
    cudaFuncSetAttribute(mega_kernel, cudaFuncAttributeMaxDynamicSharedMemorySize, SMEM_BYTES);
  }
  Params prm;
  prm.x0 = (const __nv_bfloat16*)d_in[0];
  prm.wA_qkv = (const __nv_bfloat16*)d_in[1];
  prm.wA_o = (const __nv_bfloat16*)d_in[2];
  prm.wB_qkv = (const __nv_bfloat16*)d_in[4];
  prm.wB_phi = (const __nv_bfloat16*)d_in[5];
  prm.wB_o = (const __nv_bfloat16*)d_in[6];
  prm.out = (__nv_bfloat16*)d_out;
  void *obuf = nullptr, *wf = nullptr;
  cudaGetSymbolAddress(&obuf, g_obuf);
  cudaGetSymbolAddress(&wf, g_wfold);
  CUtensorMap tm_x0 = make_map(enc, d_in[0], D_MODEL, S_LEN, 64, 128);
  CUtensorMap tm_xo = make_map(enc, d_out, D_MODEL, S_LEN, 64, 128);
  CUtensorMap tm_o = make_map(enc, obuf, D_MODEL, S_LEN, 64, 128);
  CUtensorMap tm_wf = make_map(enc, wf, 2048, D_MODEL, 64, 32);
  CUtensorMap tm_wqA = make_map(enc, d_in[1], 3 * D_MODEL, D_MODEL, 64, 32);
  CUtensorMap tm_wqB = make_map(enc, prm.wB_qkv, 3 * D_MODEL, D_MODEL, 64, 32);
  CUtensorMap tm_woA = make_map(enc, prm.wA_o, D_MODEL, D_MODEL, 64, 64);
  CUtensorMap tm_woB = make_map(enc, prm.wB_o, D_MODEL, D_MODEL, 64, 64);
  CUtensorMap tm_phi = make_map(enc, prm.wB_phi, 32, 1024, 32, 128, CU_TENSOR_MAP_SWIZZLE_64B);
  mega_kernel<<<NMAIN + NAUX, 384, SMEM_BYTES>>>(tm_x0, tm_xo, tm_o, tm_wf, tm_wqA, tm_wqB, tm_woA, tm_woB, tm_phi, prm);
}
```

```cpp
#include <cuda_runtime.h>
#include <cuda.h>
#include <cuda_bf16.h>
#include <stdint.h>

#define NLAYERS 4

#define STAG1 300
#define HPUMP1 2
#define HPUMP2 2
#define ASKEW 2
#define FPUMP 3
#define BMASK 0x1FF
#define ASITE 1
namespace {

constexpr int S_LEN = 2048, D_MODEL = 1024;
constexpr int NAUX = 4, NMAIN = 128;
constexpr int SLOT = 16384;
constexpr int QST = 24576;
constexpr int OFF_RA = 6 * SLOT, OFF_S = 10 * SLOT;
constexpr int OFF_HALO = 13 * SLOT, OFF_LNB = OFF_HALO  , OFF_ONES = OFF_HALO + 3072;
constexpr int OFF_ST = OFF_HALO + 7168  , OFF_PHI = OFF_HALO + 8192;
constexpr int OFF_BAR = 14 * SLOT;
constexpr int OFF_LNA = OFF_BAR + 1024;
constexpr int SMEM_BYTES = OFF_LNA + 2048;
#define WO_ASLOT(par) ((par) ? 0x689C7BA3689C768Cull : 0x68C97BA368C9768Cull)
constexpr unsigned long long WO_BSLOT = 0x5432105421054210ull;
__device__ __forceinline__ int kslice(int j, int i) { return i < 2 ? 2 * j + i : (i < 9 ? 2 * ((j + i - 1) & 7) : 2 * ((j + i) & 7) + 1); }
__device__ __forceinline__ int wslice(int j, int s) { return 2 * ((j + s) & 7) + (s >> 3); }
constexpr int KVH = 5 * 128 * 4;

struct __align__(128) Flag { unsigned v; unsigned pad[31]; };
struct Flags {
  Flag xready[4][16];
  Flag oready[4][16];
  Flag kvready[4][8][16];
  Flag wfready[8];
  Flag done;
  Flag epoch;
};

__device__ Flags g_flags;
__device__ __nv_bfloat16 g_obuf[S_LEN * D_MODEL];
__device__ __nv_bfloat16 g_xbuf[S_LEN * D_MODEL];
#define O_BIT(l) ((epoch * NLAYERS + (l) + 1) & 1u)
#define X_BIT(l) ((epoch * (NLAYERS - 1) + (l) + 1) & 1u)
__device__ __nv_bfloat16 g_wfold[D_MODEL * 2048];
__device__ uint4 g_halo[16 * 8 * 512];
__device__ float g_kv[2][32 * KVH];
__device__ __align__(128) uint2 g_colsum[2][1536][2];
__device__ __align__(128) uint2 g_stats[S_LEN * 8];
#define STAT_TAG(l) ((ep1 * NLAYERS + (l) + 1) & 3u)

#define RETRY_COUNT()
#define PROFL 1
#define PROFW 0
#define KVFLAG 1
#define PROFT(i) do {} while (0)
#define PROF(i) do {} while (0)

__device__ __forceinline__ uint32_t smem_u32(const void* p) { return (uint32_t)__cvta_generic_to_shared(p); }
__device__ __forceinline__ bool elect_one() {
  uint32_t p;
  asm volatile("{\n.reg .pred p;\nelect.sync _|p, 0xffffffff;\nselp.u32 %0, 1, 0, p;\n}\n" : "=r"(p));
  return p != 0;
}
__device__ __forceinline__ void mbar_init(uint32_t bar, uint32_t cnt) {
  asm volatile("mbarrier.init.shared::cta.b64 [%0], %1;" :: "r"(bar), "r"(cnt));
}
__device__ __forceinline__ void mbar_expect_tx(uint32_t bar, uint32_t bytes) {
  asm volatile("mbarrier.arrive.expect_tx.shared::cta.b64 _, [%0], %1;" :: "r"(bar), "r"(bytes) : "memory");
}
__device__ __forceinline__ void mbar_wait(uint32_t bar, uint32_t parity) {
  uint32_t ok;
  int it = 0;
  do {
    asm volatile("{\n.reg .pred p;\nmbarrier.try_wait.parity.shared::cta.b64 p, [%1], %2;\nselp.u32 %0, 1, 0, p;\n}\n"
                 : "=r"(ok) : "r"(bar), "r"(parity) : "memory");
  } while (!ok && ++it < (1 << 20));
}
__device__ __forceinline__ void mbar_wait_sl(uint32_t bar, uint32_t parity) {
  uint32_t ok;
  int it = 0;
  do {
    asm volatile("{\n.reg .pred p;\nmbarrier.try_wait.parity.shared::cta.b64 p, [%1], %2, %3;\nselp.u32 %0, 1, 0, p;\n}\n"
                 : "=r"(ok) : "r"(bar), "r"(parity), "r"(20000) : "memory");
  } while (!ok && ++it < (1 << 16));
}
__device__ __forceinline__ void mbar_arrive_local(uint32_t bar) {
  asm volatile("mbarrier.arrive.shared::cta.b64 _, [%0];" :: "r"(bar) : "memory");
}
__device__ __forceinline__ void mbar_arrive_remote(uint32_t bar, uint32_t cta_rank) {
  asm volatile("{\n.reg .b32 ra;\nmapa.shared::cluster.u32 ra, %0, %1;\nmbarrier.arrive.shared::cluster.b64 _, [ra];\n}\n"
               :: "r"(bar), "r"(cta_rank) : "memory");
}
__device__ __forceinline__ void tma_load_2d(uint32_t dst, const CUtensorMap* tm, uint32_t bar, int c0, int c1) {
  asm volatile("cp.async.bulk.tensor.2d.shared::cluster.global.mbarrier::complete_tx::bytes [%0], [%1, {%3, %4}], [%2];"
               :: "r"(dst), "l"(tm), "r"(bar), "r"(c0), "r"(c1) : "memory");
}
__device__ __forceinline__ void tma_load_2d_mc(uint32_t dst, const CUtensorMap* tm, uint32_t bar, int c0, int c1) {
  asm volatile("cp.async.bulk.tensor.2d.shared::cluster.global.mbarrier::complete_tx::bytes.multicast::cluster [%0], [%1, {%3, %4}], [%2], %5;"
               :: "r"(dst), "l"(tm), "r"(bar), "r"(c0), "r"(c1), "h"((uint16_t)3) : "memory");
}
__device__ __forceinline__ void tma_store_2d(const CUtensorMap* tm, uint32_t src, int c0, int c1) {
  asm volatile("cp.async.bulk.tensor.2d.global.shared::cta.bulk_group [%0, {%2, %3}], [%1];"
               :: "l"(tm), "r"(src), "r"(c0), "r"(c1) : "memory");
}
__device__ __forceinline__ void bulk_commit_wait() {
  asm volatile("cp.async.bulk.commit_group;\ncp.async.bulk.wait_group 0;" ::: "memory");
}
__device__ __forceinline__ void prefetch_l2(const void* p, uint32_t bytes) {
  asm volatile("cp.async.bulk.prefetch.L2.global [%0], %1;" :: "l"(p), "r"(bytes) : "memory");
}
__device__ __forceinline__ void prefetch_tmap(const CUtensorMap* tm) {
  asm volatile("prefetch.tensormap [%0];" :: "l"(tm) : "memory");
}
__device__ __forceinline__ void fence_proxy_async_global() { asm volatile("fence.proxy.async.global;" ::: "memory"); }
__device__ __forceinline__ void fence_proxy_async_smem() { asm volatile("fence.proxy.async.shared::cta;" ::: "memory"); }
__device__ __forceinline__ unsigned ld_relaxed(const unsigned* p) {
  unsigned v;
  asm volatile("ld.relaxed.gpu.global.u32 %0, [%1];" : "=r"(v) : "l"(p) : "memory");
  return v;
}
__device__ __forceinline__ void fence_acquire() { asm volatile("fence.acquire.gpu;" ::: "memory"); }
__device__ __forceinline__ void wait_flag(const unsigned* p, unsigned target) {
  int it = 0;
  while ((int)(ld_relaxed(p) - target) < 0 && ++it < (1 << 20)) {}
  fence_acquire();
}
__device__ __forceinline__ void signal_release(unsigned* p) {
  asm volatile("red.release.gpu.global.add.u32 [%0], 1;" :: "l"(p) : "memory");
}
template <int ID, int N> __device__ __forceinline__ void bar_arrive() { asm volatile("bar.arrive %0, %1;" :: "n"(ID), "n"(N) : "memory"); }
template <int ID, int N> __device__ __forceinline__ void bar_sync() { asm volatile("bar.sync %0, %1;" :: "n"(ID), "n"(N) : "memory"); }
__device__ __forceinline__ void bar_wg(int wg) { asm volatile("bar.sync %0, 128;" :: "r"(2 + wg) : "memory"); }
__device__ __forceinline__ void cluster_sync() {
  asm volatile("barrier.cluster.arrive.relaxed.aligned;\nbarrier.cluster.wait.aligned;" ::: "memory");
}
__device__ __forceinline__ void cluster_wait() { asm volatile("barrier.cluster.wait.acquire.aligned;" ::: "memory"); }
enum { BAR_KV = 4  , BAR_O = 7  , BAR_WF = 12  , BAR_SKEW = 13 };

__device__ __forceinline__ void wgmma_fence() { asm volatile("wgmma.fence.sync.aligned;" ::: "memory"); }
__device__ __forceinline__ void wgmma_commit() { asm volatile("wgmma.commit_group.sync.aligned;" ::: "memory"); }
template <int N> __device__ __forceinline__ void wgmma_wait() { asm volatile("wgmma.wait_group.sync.aligned %0;" :: "n"(N) : "memory"); }

template <int scale_d, int tnsp_b = 1> __device__ __forceinline__ void wgmma_n192(float* d, uint64_t descA, uint64_t descB) {
  asm volatile("{\n.reg .pred p;\nsetp.ne.b32 p, %98, 0;\n"
               "wgmma.mma_async.sync.aligned.m64n192k16.f32.bf16.bf16 {%0,%1,%2,%3,%4,%5,%6,%7,%8,%9,%10,%11,%12,%13,%14,%15,%16,%17,%18,%19,%20,%21,%22,%23,%24,%25,%26,%27,%28,%29,%30,%31,%32,%33,%34,%35,%36,%37,%38,%39,%40,%41,%42,%43,%44,%45,%46,%47,%48,%49,%50,%51,%52,%53,%54,%55,%56,%57,%58,%59,%60,%61,%62,%63,%64,%65,%66,%67,%68,%69,%70,%71,%72,%73,%74,%75,%76,%77,%78,%79,%80,%81,%82,%83,%84,%85,%86,%87,%88,%89,%90,%91,%92,%93,%94,%95}, %96, %97, p, 1, 1, 0, %99;\n}\n"
               : "+f"(d[0]), "+f"(d[1]), "+f"(d[2]), "+f"(d[3]), "+f"(d[4]), "+f"(d[5]), "+f"(d[6]), "+f"(d[7]), "+f"(d[8]), "+f"(d[9]), "+f"(d[10]), "+f"(d[11]), "+f"(d[12]), "+f"(d[13]), "+f"(d[14]), "+f"(d[15]), "+f"(d[16]), "+f"(d[17]), "+f"(d[18]), "+f"(d[19]), "+f"(d[20]), "+f"(d[21]), "+f"(d[22]), "+f"(d[23]), "+f"(d[24]), "+f"(d[25]), "+f"(d[26]), "+f"(d[27]), "+f"(d[28]), "+f"(d[29]), "+f"(d[30]), "+f"(d[31]), "+f"(d[32]), "+f"(d[33]), "+f"(d[34]), "+f"(d[35]), "+f"(d[36]), "+f"(d[37]), "+f"(d[38]), "+f"(d[39]), "+f"(d[40]), "+f"(d[41]), "+f"(d[42]), "+f"(d[43]), "+f"(d[44]), "+f"(d[45]), "+f"(d[46]), "+f"(d[47]), "+f"(d[48]), "+f"(d[49]), "+f"(d[50]), "+f"(d[51]), "+f"(d[52]), "+f"(d[53]), "+f"(d[54]), "+f"(d[55]), "+f"(d[56]), "+f"(d[57]), "+f"(d[58]), "+f"(d[59]), "+f"(d[60]), "+f"(d[61]), "+f"(d[62]), "+f"(d[63]), "+f"(d[64]), "+f"(d[65]), "+f"(d[66]), "+f"(d[67]), "+f"(d[68]), "+f"(d[69]), "+f"(d[70]), "+f"(d[71]), "+f"(d[72]), "+f"(d[73]), "+f"(d[74]), "+f"(d[75]), "+f"(d[76]), "+f"(d[77]), "+f"(d[78]), "+f"(d[79]), "+f"(d[80]), "+f"(d[81]), "+f"(d[82]), "+f"(d[83]), "+f"(d[84]), "+f"(d[85]), "+f"(d[86]), "+f"(d[87]), "+f"(d[88]), "+f"(d[89]), "+f"(d[90]), "+f"(d[91]), "+f"(d[92]), "+f"(d[93]), "+f"(d[94]), "+f"(d[95])
               : "l"(descA), "l"(descB), "n"(scale_d), "n"(tnsp_b));
}
template <int scale_d> __device__ __forceinline__ void wgmma_n128(float* d, uint64_t descA, uint64_t descB) {
  asm volatile("{\n.reg .pred p;\nsetp.ne.b32 p, %66, 0;\n"
               "wgmma.mma_async.sync.aligned.m64n128k16.f32.bf16.bf16 {%0,%1,%2,%3,%4,%5,%6,%7,%8,%9,%10,%11,%12,%13,%14,%15,%16,%17,%18,%19,%20,%21,%22,%23,%24,%25,%26,%27,%28,%29,%30,%31,%32,%33,%34,%35,%36,%37,%38,%39,%40,%41,%42,%43,%44,%45,%46,%47,%48,%49,%50,%51,%52,%53,%54,%55,%56,%57,%58,%59,%60,%61,%62,%63}, %64, %65, p, 1, 1, 0, 1;\n}\n"
               : "+f"(d[0]), "+f"(d[1]), "+f"(d[2]), "+f"(d[3]), "+f"(d[4]), "+f"(d[5]), "+f"(d[6]), "+f"(d[7]), "+f"(d[8]), "+f"(d[9]), "+f"(d[10]), "+f"(d[11]), "+f"(d[12]), "+f"(d[13]), "+f"(d[14]), "+f"(d[15]), "+f"(d[16]), "+f"(d[17]), "+f"(d[18]), "+f"(d[19]), "+f"(d[20]), "+f"(d[21]), "+f"(d[22]), "+f"(d[23]), "+f"(d[24]), "+f"(d[25]), "+f"(d[26]), "+f"(d[27]), "+f"(d[28]), "+f"(d[29]), "+f"(d[30]), "+f"(d[31]), "+f"(d[32]), "+f"(d[33]), "+f"(d[34]), "+f"(d[35]), "+f"(d[36]), "+f"(d[37]), "+f"(d[38]), "+f"(d[39]), "+f"(d[40]), "+f"(d[41]), "+f"(d[42]), "+f"(d[43]), "+f"(d[44]), "+f"(d[45]), "+f"(d[46]), "+f"(d[47]), "+f"(d[48]), "+f"(d[49]), "+f"(d[50]), "+f"(d[51]), "+f"(d[52]), "+f"(d[53]), "+f"(d[54]), "+f"(d[55]), "+f"(d[56]), "+f"(d[57]), "+f"(d[58]), "+f"(d[59]), "+f"(d[60]), "+f"(d[61]), "+f"(d[62]), "+f"(d[63])
               : "l"(descA), "l"(descB), "n"(scale_d));
}
template <int scale_d> __device__ __forceinline__ void wgmma_n32(float* d, uint64_t descA, uint64_t descB) {
  asm volatile("{\n.reg .pred p;\nsetp.ne.b32 p, %18, 0;\n"
               "wgmma.mma_async.sync.aligned.m64n32k16.f32.bf16.bf16 {%0,%1,%2,%3,%4,%5,%6,%7,%8,%9,%10,%11,%12,%13,%14,%15}, %16, %17, p, 1, 1, 0, 1;\n}\n"
               : "+f"(d[0]), "+f"(d[1]), "+f"(d[2]), "+f"(d[3]), "+f"(d[4]), "+f"(d[5]), "+f"(d[6]), "+f"(d[7]), "+f"(d[8]), "+f"(d[9]), "+f"(d[10]), "+f"(d[11]), "+f"(d[12]), "+f"(d[13]), "+f"(d[14]), "+f"(d[15])
               : "l"(descA), "l"(descB), "n"(scale_d));
}
template <int scale_d, int tnsp_a> __device__ __forceinline__ void wgmma_n40(float* d, uint64_t descA, uint64_t descB) {
  asm volatile("{\n.reg .pred p;\nsetp.ne.b32 p, %22, 0;\n"
               "wgmma.mma_async.sync.aligned.m64n40k16.f32.bf16.bf16 {%0,%1,%2,%3,%4,%5,%6,%7,%8,%9,%10,%11,%12,%13,%14,%15,%16,%17,%18,%19}, %20, %21, p, 1, 1, %23, 1;\n}\n"
               : "+f"(d[0]), "+f"(d[1]), "+f"(d[2]), "+f"(d[3]), "+f"(d[4]), "+f"(d[5]), "+f"(d[6]), "+f"(d[7]), "+f"(d[8]), "+f"(d[9]), "+f"(d[10]), "+f"(d[11]), "+f"(d[12]), "+f"(d[13]), "+f"(d[14]), "+f"(d[15]), "+f"(d[16]), "+f"(d[17]), "+f"(d[18]), "+f"(d[19])
               : "l"(descA), "l"(descB), "n"(scale_d), "n"(tnsp_a));
}
__device__ __forceinline__ uint64_t make_desc(uint32_t addr, uint32_t lbo_bytes, uint32_t sbo_bytes) {
  return (uint64_t)((addr & 0x3FFFF) >> 4) | ((uint64_t)(lbo_bytes >> 4) << 16) | ((uint64_t)(sbo_bytes >> 4) << 32) | (1ull << 62);
}

__device__ __forceinline__ void ldsm_x4(uint32_t addr, uint32_t& r0, uint32_t& r1, uint32_t& r2, uint32_t& r3) {
  asm volatile("ldmatrix.sync.aligned.m8n8.x4.shared.b16 {%0,%1,%2,%3}, [%4];" : "=r"(r0), "=r"(r1), "=r"(r2), "=r"(r3) : "r"(addr) : "memory");
}
__device__ __forceinline__ void ldsm_x4_t(uint32_t addr, uint32_t& r0, uint32_t& r1, uint32_t& r2, uint32_t& r3) {
  asm volatile("ldmatrix.sync.aligned.m8n8.x4.trans.shared.b16 {%0,%1,%2,%3}, [%4];" : "=r"(r0), "=r"(r1), "=r"(r2), "=r"(r3) : "r"(addr) : "memory");
}
__device__ __forceinline__ void stsm_x4(uint32_t addr, uint32_t r0, uint32_t r1, uint32_t r2, uint32_t r3) {
  asm volatile("stmatrix.sync.aligned.m8n8.x4.shared.b16 [%0], {%1,%2,%3,%4};" :: "r"(addr), "r"(r0), "r"(r1), "r"(r2), "r"(r3) : "memory");
}
__device__ __forceinline__ void sts128(uint32_t addr, uint32_t a, uint32_t b, uint32_t c, uint32_t d) {
  asm volatile("st.shared.v4.u32 [%0], {%1,%2,%3,%4};" :: "r"(addr), "r"(a), "r"(b), "r"(c), "r"(d) : "memory");
}
__device__ __forceinline__ float lds32f(uint32_t addr) {
  float v;
  asm volatile("ld.shared.f32 %0, [%1];" : "=f"(v) : "r"(addr) : "memory");
  return v;
}
__device__ __forceinline__ void sts32f(uint32_t addr, float a) {
  asm volatile("st.shared.f32 [%0], %1;" :: "r"(addr), "f"(a) : "memory");
}
__device__ __forceinline__ void mma_bf16(float (&c)[4], uint32_t a0, uint32_t a1, uint32_t a2, uint32_t a3, uint32_t b0, uint32_t b1) {
  asm volatile("mma.sync.aligned.m16n8k16.row.col.f32.bf16.bf16.f32 {%0,%1,%2,%3}, {%4,%5,%6,%7}, {%8,%9}, {%0,%1,%2,%3};"
               : "+f"(c[0]), "+f"(c[1]), "+f"(c[2]), "+f"(c[3]) : "r"(a0), "r"(a1), "r"(a2), "r"(a3), "r"(b0), "r"(b1));
}
__device__ __forceinline__ uint32_t pack_bf16(float lo, float hi) {
  uint32_t r;
  asm("cvt.rn.bf16x2.f32 %0, %1, %2;" : "=r"(r) : "f"(hi), "f"(lo));
  return r;
}
__device__ __forceinline__ float bf_lo(uint32_t v) { return __uint_as_float(v << 16); }
__device__ __forceinline__ float bf_hi(uint32_t v) { return __uint_as_float(v & 0xFFFF0000u); }
__device__ __forceinline__ void split3(float x, uint32_t& h, uint32_t& m, uint32_t& l) {
  h = pack_bf16(x, 0.f); x -= bf_lo(h);
  m = pack_bf16(x, 0.f); x -= bf_lo(m);
  l = pack_bf16(x, 0.f);
}
__device__ __forceinline__ float ex2(float x) { float r; asm("ex2.approx.ftz.f32 %0, %1;" : "=f"(r) : "f"(x)); return r; }
__device__ __forceinline__ float rcp_fast(float x) { float r; asm("rcp.approx.ftz.f32 %0, %1;" : "=f"(r) : "f"(x)); return r; }
__device__ __forceinline__ void red_v4(float* p, float a, float b, float c, float d) {
  asm volatile("red.global.add.v4.f32 [%0], {%1, %2, %3, %4};" :: "l"(p), "f"(a), "f"(b), "f"(c), "f"(d) : "memory");
}
__device__ __forceinline__ uint4 ld_ll(const uint4* p) {
  uint4 v;
  asm volatile("{\n.reg .b64 a, b;\nld.relaxed.gpu.global.v2.b64 {a, b}, [%4];\nmov.b64 {%0, %1}, a;\nmov.b64 {%2, %3}, b;\n}\n"
               : "=r"(v.x), "=r"(v.y), "=r"(v.z), "=r"(v.w) : "l"(p) : "memory");
  return v;
}
__device__ __forceinline__ void st_b64(uint2* p, uint32_t a, uint32_t b) {
  asm volatile("{\n.reg .b64 v;\nmov.b64 v, {%1, %2};\nst.relaxed.gpu.global.b64 [%0], v;\n}\n" :: "l"(p), "r"(a), "r"(b) : "memory");
}
__device__ __forceinline__ void st_b128(uint4* p, uint32_t a, uint32_t b, uint32_t c, uint32_t d) {
  asm volatile("{\n.reg .b128 v;\nmov.b128 v, {%1, %2, %3, %4};\nst.relaxed.gpu.global.b128 [%0], v;\n}\n" :: "l"(p), "r"(a), "r"(b), "r"(c), "r"(d) : "memory");
}
__device__ __forceinline__ uint4 ld_b128(const uint4* p) {
  uint4 v;
  asm volatile("{\n.reg .b128 v;\nld.relaxed.gpu.global.b128 v, [%4];\nmov.b128 {%0, %1, %2, %3}, v;\n}\n" : "=r"(v.x), "=r"(v.y), "=r"(v.z), "=r"(v.w) : "l"(p) : "memory");
  return v;
}

constexpr float LOG2E = 1.4426950408889634f;

struct Params {
  const __nv_bfloat16* x0;
  const __nv_bfloat16* wA_qkv;
  const __nv_bfloat16* wA_o;
  const __nv_bfloat16* wB_qkv;
  const __nv_bfloat16* wB_phi;
  const __nv_bfloat16* wB_o;
  __nv_bfloat16* out;
};

#define ACC_DEF(d, n) _Pragma("unroll") for (int i_ = 0; i_ < (n); i_++) asm volatile("" : "=f"(d[i_]))
#define ACC_FENCE(d, n) _Pragma("unroll") for (int i_ = 0; i_ < (n); i_++) asm volatile("" : "+f"(d[i_]) :: "memory")
#define PIN(a, n) _Pragma("unroll") for (int i_ = 0; i_ < (n); i_++) asm volatile("" : "+f"((a)[i_]))
#define PINU(a, n) _Pragma("unroll") for (int i_ = 0; i_ < (n); i_++) asm volatile("" : "+r"((a)[i_]))

#define STAGE64(acc, off, p0, KIND) { \
    uint32_t w_[4][4]; \
    _Pragma("unroll") for (int j_ = 0; j_ < 4; j_++) { \
      const int o_ = (off) + j_ * 8; \
      w_[j_][0] = pack_bf16(rs0 * acc[o_ + 0], rs0 * acc[o_ + 1]); \
      w_[j_][1] = pack_bf16(rs1 * acc[o_ + 2], rs1 * acc[o_ + 3]); \
      w_[j_][2] = pack_bf16(rs0 * acc[o_ + 4], rs0 * acc[o_ + 5]); \
      w_[j_][3] = pack_bf16(rs1 * acc[o_ + 6], rs1 * acc[o_ + 7]); \
    } \
    if (hsend) { \
      _Pragma("unroll") for (int j_ = 0; j_ < 4; j_++) { \
        w_[j_][0] = (w_[j_][0] & ~1u) | hbit; \
        st_b128(hbase + lane + ((KIND) * 4 + j_) * 32, w_[j_][0], w_[j_][1], w_[j_][2], w_[j_][3]); \
      } \
    } \
    _Pragma("unroll") for (int j_ = 0; j_ < 4; j_++) \
      stsm_x4((KIND) ? (p0) + (j_ >> 1) * 8192 + (srowoff >> 1) + ((((uint32_t)(j_ & 1) << 5) + lhi) ^ lsw2) \
                     : (p0) + srowoff + ((((uint32_t)j_ << 5) + lhi) ^ lsw), \
              w_[j_][0], w_[j_][1], w_[j_][2], w_[j_][3]); \
  }
#define RW(j) (((j) >> 1) * 4 + ((j) & 1))
__device__ __forceinline__ float rmax16(const float* p) {
  float m[4];
#pragma unroll
  for (int j = 0; j < 4; j++) m[j] = fmaxf(fmaxf(p[RW(j)], p[RW(j + 4)]), fmaxf(p[RW(j + 8)], p[RW(j + 12)]));
  const float r = fmaxf(fmaxf(m[0], m[1]), fmaxf(m[2], m[3]));
  return fmaxf(r, __shfl_xor_sync(0xffffffffu, r, 1));
}
__device__ __forceinline__ float rmin16(const float* p) {
  float m[4];
#pragma unroll
  for (int j = 0; j < 4; j++) m[j] = fminf(fminf(p[RW(j)], p[RW(j + 4)]), fminf(p[RW(j + 8)], p[RW(j + 12)]));
  const float r = fminf(fminf(m[0], m[1]), fminf(m[2], m[3]));
  return fminf(r, __shfl_xor_sync(0xffffffffu, r, 1));
}
__device__ __forceinline__ float exps16(float* o, const float* p, float c, float b) {
  float s[4] = {0.f, 0.f, 0.f, 0.f};
#pragma unroll
  for (int j = 0; j < 16; j++) { o[j] = ex2(fmaf(p[RW(j)], c, b)); s[j & 3] += o[j]; }
  return (s[0] + s[1]) + (s[2] + s[3]);
}
__device__ __forceinline__ void store16(const float* e, float sum, uint32_t dst, uint32_t dsw, int c0) {
  const float inv = rcp_fast(sum + __shfl_xor_sync(0xffffffffu, sum, 1));
#pragma unroll
  for (int j = 0; j < 2; j++)
    sts128(dst + (((c0 + j) << 4) ^ dsw), pack_bf16(e[j * 8] * inv, e[j * 8 + 1] * inv), pack_bf16(e[j * 8 + 2] * inv, e[j * 8 + 3] * inv),
           pack_bf16(e[j * 8 + 4] * inv, e[j * 8 + 5] * inv), pack_bf16(e[j * 8 + 6] * inv, e[j * 8 + 7] * inv));
}
__device__ __forceinline__ void expp16(uint32_t* o, const float* p, float c, float b) {
#pragma unroll
  for (int j = 0; j < 8; j++) o[j] = pack_bf16(ex2(fmaf(p[4 * j], c, b)), ex2(fmaf(p[4 * j + 1], c, b)));
}
#define SCHED_FENCE() asm volatile("pmevent 0;" ::: "memory")

__global__ void __cluster_dims__(2, 1, 1) __launch_bounds__(384, 1)
mega_kernel(const __grid_constant__ CUtensorMap tm_x0, const __grid_constant__ CUtensorMap tm_xo, const __grid_constant__ CUtensorMap tm_xb,
            const __grid_constant__ CUtensorMap tm_o, const __grid_constant__ CUtensorMap tm_wf,
            const __grid_constant__ CUtensorMap tm_wqA, const __grid_constant__ CUtensorMap tm_wqB,
            const __grid_constant__ CUtensorMap tm_woA, const __grid_constant__ CUtensorMap tm_woB,
            const __grid_constant__ CUtensorMap tm_phi, const Params prm) {
  extern __shared__ __align__(1024) uint8_t smem_raw[];
  const uint32_t sbase = smem_u32(smem_raw);
  const uint32_t bar_full = sbase + OFF_BAR;
  const uint32_t bar_done = bar_full + 384;
  const uint32_t bar_stat = bar_full + 768, bar_stat2 = bar_full + 776, bar_epi = bar_full + 784, bar_phi = bar_full + 936  ;
  const uint32_t bar_xr = bar_full + 800, bar_lx = bar_full + 808, bar_kvf = bar_full + 816  , bar_stg = bar_full + 832, bar_o1s = bar_full + 840;
  const uint32_t bar_chk = bar_full + 848;

  const int warp = __shfl_sync(0xffffffffu, threadIdx.x >> 5, 0), lane = threadIdx.x & 31;
  uint32_t rank;
  asm volatile("mov.u32 %0, %%cluster_ctarank;" : "=r"(rank));
  const int cta = (int)blockIdx.x - NAUX;
  const int cl = cta >> 1;
  const int jj = cl & 7, cc = cl >> 3;
  const int mm = cc * 2 + (int)rank;

  unsigned epoch;
  asm volatile("ld.relaxed.gpu.global.u32 %0, [%1];" : "=r"(epoch) : "l"(&g_flags.epoch.v) : "memory");
  const unsigned ep1 = epoch + 1;

  if (cta >= 0) {
    {
      const int tx = threadIdx.x;
      const __nv_bfloat16* pf = (tx < 128) ? prm.x0 + (size_t)(mm * 128 + tx) * D_MODEL + jj * 128
                                           : prm.wA_qkv + (size_t)(jj * 128 + (tx & 63)) * 3072 + ((tx - 128) >> 6) * 1024 + jj * 128 + rank * 64;
      if (tx < 320) asm volatile("prefetch.global.L2 [%0];" :: "l"(pf));
      else if (tx == 320) prefetch_tmap(&tm_x0);
      else if (tx == 352) prefetch_tmap(&tm_wqA);
    }
    if (threadIdx.x < 48) {
      if (threadIdx.x == 0) {
        mbar_init(bar_stat, 2); mbar_init(bar_stat2, 1); mbar_init(bar_epi, 8); mbar_init(bar_phi, 1); mbar_init(bar_phi + 8, 1);
        mbar_init(bar_xr, 1); mbar_init(bar_lx, 8); mbar_init(bar_kvf, 1); mbar_init(bar_kvf + 8, 1); mbar_init(bar_stg, 8); mbar_init(bar_o1s, 2);
      }
      mbar_init(bar_full + threadIdx.x * 8, ((threadIdx.x & ~3u) == 4 || threadIdx.x > 40) ? 2 : 1); mbar_init(bar_done + threadIdx.x * 8, 16);
      if (threadIdx.x < 11) mbar_init(bar_chk + threadIdx.x * 8, 1);
      asm volatile("fence.mbarrier_init.release.cluster;" ::: "memory");
    }
    __syncthreads();
    asm volatile("barrier.cluster.arrive.relaxed.aligned;" ::: "memory");
  }

  if (cta < 0) {
    const uint32_t buf = sbase + warp * SLOT, bar = sbase + OFF_BAR + warp * 16;
    const uint32_t lsw = (lane & 7) << 4, lhi = (lane >> 4) << 4, lrow = (lane & 15) * 128;
    const bool el = elect_one();
    if (el) {
      mbar_init(bar, 1); mbar_init(bar + 8, 1);
      asm volatile("fence.mbarrier_init.release.cluster;" ::: "memory");
    }
#pragma unroll 1
    for (int rd = 0; rd < (NLAYERS > 1 ? 5 : 2); rd++) {
      if (rd >= 2 && warp >= 8) break;
      const int tk = rd < 2 ? blockIdx.x * 12 + warp : blockIdx.x * 8 + warp;
      const int half = tk & 1;
      const int blk = rd < 2 ? (tk >> 1) * 2 + rd : (rd == 2 ? 32 + (tk >> 1) : (tk >> 1) * 2 + rd - 3);
      const CUtensorMap* tm = rd < 2 ? &tm_wqA : (rd == 2 ? &tm_wqB : &tm_wf);
      const int j0 = (blk & 15) >> 1;
#define AUX_LOAD(n) { const uint32_t d_ = buf + ((n) & 1) * 8192, b_ = bar + ((n) & 1) * 8; const int r_ = kslice(j0, 2 * (n) + half) * 64; \
        mbar_expect_tx(b_, 8192); tma_load_2d(d_, tm, b_, blk * 64, r_); tma_load_2d(d_ + 4096, tm, b_, blk * 64, r_ + 32); }
      if (el) {
        if (rd == 3) { wait_flag(&g_flags.wfready[j0].v, ep1 * 16); fence_proxy_async_global(); }
        AUX_LOAD(0); AUX_LOAD(1);
      }
      __syncwarp();
      float cs[8][4];
#pragma unroll
      for (int i = 0; i < 8; i++) cs[i][0] = cs[i][1] = cs[i][2] = cs[i][3] = 0.f;
#pragma unroll 1
      for (int n = 0; n < 8; n++) {
        const uint32_t tb = buf + (n & 1) * 8192 + lrow;
        mbar_wait(bar + (n & 1) * 8, (n >> 1) & 1);
#pragma unroll
        for (int i = 0; i < 16; i++) {
          uint32_t b0, b1, b2, b3;
          ldsm_x4_t(tb + (i >> 2) * 2048 + (((i & 3) * 32 + lhi) ^ lsw), b0, b1, b2, b3);
          mma_bf16(cs[2 * (i & 3)], 0x3F803F80u, 0x3F803F80u, 0x3F803F80u, 0x3F803F80u, b0, b1);
          mma_bf16(cs[2 * (i & 3) + 1], 0x3F803F80u, 0x3F803F80u, 0x3F803F80u, 0x3F803F80u, b2, b3);
        }
        __syncwarp();
        if (el && n < 6) AUX_LOAD(n + 2);
      }
      if (lane < 4) {
#pragma unroll
        for (int i = 0; i < 8; i++) st_b64(&g_colsum[rd >= 2][blk * 32 + i * 4 + lane][half], __float_as_uint(cs[i][0]), (__float_as_uint(cs[i][1]) & ~3u) | (ep1 & 3));
      }
      __syncwarp();
    }
  } else if (warp >= 8) {
    asm volatile("setmaxnreg.dec.sync.aligned.u32 40;");
    if (warp == 8) {
      const bool el = elect_one();
      cluster_wait();
      if (el) {
#pragma unroll 1
        for (int l = 0; l < NLAYERS; l++) {
          const uint32_t par = l & 1;
          const CUtensorMap* tqk = par ? &tm_wf : &tm_wqA;
          const CUtensorMap* tv = par ? &tm_wqB : &tm_wqA;
          const CUtensorMap* two = par ? &tm_woB : &tm_woA;
          if (l == 1) { wait_flag(&g_flags.wfready[jj].v, ep1 * 16); fence_proxy_async_global(); }
#pragma unroll 1
          for (int u = 0; u < 32; u++) {
            if (u >= 4) mbar_wait_sl(bar_done + (u - 4) * 8, par);
            else if (l) mbar_wait_sl(bar_done + (43 + u + (u >> 1)) * 8, par ^ 1);
            else if (u == 1) __nanosleep(STAG1);
            else if (u == 2) mbar_wait_sl(bar_full, 0);
            const uint32_t fb = bar_full + u * 8;
            const bool res = u < 4 ? (l || u >= 2) : (u < 8 || (u >= 18 && u < 22));
            mbar_expect_tx(fb, res ? QST : QST + SLOT);
            const int row = kslice(jj, u < 4 ? u & 1 : (u < 18 ? u - 2 : (u < 22 ? u - 6 : u - 20))) * 64 + (int)rank * 32;
            const int col = jj * 128 + (u < 4 ? u >> 1 : (u >= 18)) * 64;
            const uint32_t dst = sbase + (u & 3) * QST + rank * 4096;
            tma_load_2d_mc(dst, tqk, fb, col, row);
            tma_load_2d_mc(dst + 8192, tqk, fb, col + 1024, row);
            tma_load_2d_mc(dst + 16384, tv, fb, col + 2048, row);
          }
#pragma unroll 1
          for (int s = 0; s < 16; s++) {
            if (s < 5) { if (s != 2 && s != 4) mbar_wait_sl(bar_done + (28 + s) * 8, par); }
            else if (s != 14) mbar_wait_sl(bar_done + (27 + s - (s == 15)) * 8, par);
            if (s == 13) mbar_wait_sl(bar_o1s, par);
            const uint32_t fb = bar_full + (32 + s) * 8;
            mbar_expect_tx(fb, (s && s < 8) ? 2 * SLOT : SLOT);
            tma_load_2d_mc(sbase + rank * 8192 + (uint32_t)((WO_BSLOT >> (4 * s)) & 15) * SLOT, two, fb, jj * 128 + (int)rank * 64, wslice(jj, s) * 64);
          }
        }
      }
      __syncwarp();
    } else if (warp == 9) {
      const bool el = elect_one();
      if (el) {
        tma_load_2d(sbase + OFF_S, &tm_x0, bar_full, jj * 128, mm * 128);
        __nanosleep(STAG1);
        tma_load_2d(sbase + OFF_S + SLOT, &tm_x0, bar_full + 8, jj * 128 + 64, mm * 128);
      }
      mbar_wait_sl(bar_full, 0);
      const size_t poff = (size_t)(mm * 128 + (lane >> 3) * 32 + (jj & 3) * 8) * D_MODEL + ((jj + lane + 1) & 7) * 128 + (jj >> 2) * 16;
#define POLL_TILE(i, buf, bit) \
      if (!((rdy >> (i)) & 1)) { \
        const unsigned* pp = reinterpret_cast<const unsigned*>((buf) + poff); \
        unsigned v0 = ld_relaxed(pp); \
        __nanosleep(150); \
        unsigned v1 = ld_relaxed(pp); \
        _Pragma("unroll 1") for (int it = 0; it < (1 << 18); it++) { \
          uint32_t ok = __ballot_sync(0xffffffffu, ((v0 ^ (bit)) & 1) == 0); \
          rdy = ok & (ok >> 8) & (ok >> 16) & (ok >> 24); \
          if ((rdy >> (i)) & 1) break; \
          v0 = ld_relaxed(pp); \
          ok = __ballot_sync(0xffffffffu, ((v1 ^ (bit)) & 1) == 0); \
          rdy = ok & (ok >> 8) & (ok >> 16) & (ok >> 24); \
          if ((rdy >> (i)) & 1) break; \
          v1 = ld_relaxed(pp); \
        } \
      }
#pragma unroll 1
      for (int l = 0; l < NLAYERS; l++) {
        const uint32_t par = l & 1;
        const CUtensorMap* tx = l ? &tm_xb : &tm_x0;
        uint32_t rdy = l ? 0 : 0xFF;
        if (l) mbar_wait_sl(bar_done + 47 * 8, par ^ 1);
#pragma unroll 1
        for (int u = 4; u < 8; u++) {
          POLL_TILE(u - 4, g_xbuf, X_BIT(l - 1));
          if (el) {
            if (u == 4) PROFT(320 + l * 16);
            mbar_expect_tx(bar_chk + (u - 4) * 8, SLOT);
            tma_load_2d(sbase + OFF_RA + (u & 3) * SLOT, tx, bar_chk + (u - 4) * 8, kslice(jj, u - 2) * 64, mm * 128);
          }
        }
        if (el) {
#pragma unroll 1
          for (int u = 8; u < 34; u++) {
            if (u == 18) u = 22;
            mbar_wait_sl(bar_done + (u - 4) * 8, par);
            if (u == 8 && l) { wait_flag(&g_flags.xready[l][mm].v, ep1 * 8); fence_proxy_async_global(); }
            if (u == 32) mbar_expect_tx(bar_xr, 2 * SLOT);
            tma_load_2d(sbase + OFF_RA + (u & 3) * SLOT, tx, u < 32 ? bar_full + u * 8 : bar_xr, kslice(jj, u < 18 ? u - 2 : (u < 32 ? u - 20 : u - 32)) * 64, mm * 128);
            if (l == 0 && u < 16) prefetch_l2((const char*)prm.wB_qkv + (size_t)(cta * 8 + u - 8) * 6144 + 2048, 4096);
            if (l == 0 && u < 13 && NLAYERS > 1) {
              if (u == 8) { mbar_expect_tx(bar_phi, SLOT + 8192); tma_load_2d(sbase + OFF_PHI, &tm_phi, bar_phi, 0, jj * 128); }
              else tma_load_2d(sbase + 12 * SLOT + (u - 9) * 4096, &tm_wqB, bar_phi, jj * 128 + ((u - 9) >> 1) * 64, mm * 64 + ((u - 9) & 1) * 32);
            }
            if (l < 2 && u >= 22 && u < 26) prefetch_l2((const char*)(l ? prm.wB_o : prm.wA_o) + (size_t)cta * 16384 + (u - 22) * 4096, 4096);
          }
          wait_flag(&g_flags.oready[l][mm].v, ep1 * 8);
          fence_proxy_async_global();
          PROFT(321 + l * 16);
#pragma unroll 1
          for (int s = 1; s < 8; s++) {
            if (s == 1) mbar_wait_sl(bar_done + 30 * 8, par);
            else if (s == 2) mbar_wait_sl(bar_lx, par);
            else if (s == 4) mbar_wait_sl(bar_done + (31 + par) * 8, par);
            else if (s == 5) mbar_wait_sl(par ? bar_epi : bar_done + 32 * 8, par);
            else if (s > 5) mbar_wait_sl(bar_done + (27 + s) * 8, par);
            tma_load_2d(sbase + (uint32_t)((WO_ASLOT(par) >> (4 * s)) & 15) * SLOT, &tm_o, bar_full + (32 + s) * 8, wslice(jj, s) * 64, mm * 128);
          }
        }
        __syncwarp();
        rdy = 0;
        mbar_wait_sl(bar_epi, par);
#pragma unroll 1
        for (int s = 9; s < 16; s++) {
          POLL_TILE(s - 9, g_obuf + 64, O_BIT(l));
          if (s >= 11) mbar_wait_sl(bar_done + (24 + s) * 8, par);
          if (el) {
            if (s == 9) PROFT(322 + l * 16);
            mbar_expect_tx(bar_chk + (s - 5) * 8, SLOT);
            tma_load_2d(sbase + (uint32_t)((WO_ASLOT(par) >> (4 * s)) & 15) * SLOT, &tm_o, bar_chk + (s - 5) * 8, wslice(jj, s) * 64, mm * 128);
          }
        }
      }
      __syncwarp();
      cluster_wait();
    } else {
      const int hw = warp - 10;
      const bool el = elect_one();
      cluster_wait();
      if (hw == 0) {
        mbar_wait_sl(bar_full + 8, 0);
        if (lane < 7) prefetch_tmap(lane == 0 ? &tm_xb : lane == 1 ? &tm_o : lane == 2 ? &tm_wf : lane == 3 ? &tm_wqB : lane == 4 ? &tm_woA : lane == 5 ? &tm_woB : &tm_phi);
      } else {
#pragma unroll 1
        for (int b = 0; b < 2; b++) {
          float4* z = reinterpret_cast<float4*>(g_kv[b] + (jj * 4) * KVH + mm * (4 * KVH / 16)) + lane;
#pragma unroll
          for (int i = 0; i < 5; i++) z[i * 32] = make_float4(0.f, 0.f, 0.f, 0.f);
        }
      }
      uint32_t chkp = 0;
#define CHECK_TILES(c0, c1, bit, skip) \
      _Pragma("unroll 1") for (int c = (c0); c < (c1); c++) { \
        const uint32_t tile = sbase + (c < 4 ? 6 + c : (uint32_t)((WO_ASLOT(l & 1) >> (4 * c + 20)) & 15)) * SLOT; \
        _Pragma("unroll 1") for (int it = 0; it < (1 << 12); it++) { \
          mbar_wait_sl(bar_chk + c * 8, (chkp >> c) & 1); \
          chkp ^= 1u << c; \
          if (el && (c == 0 || c == 4)) PROFT(488 + l * 2 + (c >> 2)); \
          if (skip) break; \
          uint32_t a1 = 1, o1 = 0; \
          _Pragma("unroll") for (int i = 0; i < 16; i++) { \
            uint32_t w; \
            asm volatile("ld.shared.u32 %0, [%1];" : "=r"(w) : "r"(tile + i * 1024 + (lane & 7) * 132 + (lane >> 3) * 32) : "memory"); \
            a1 &= w; o1 |= w; \
          } \
          if (__all_sync(0xffffffffu, (((bit) ? a1 : ~o1) & 1) != 0)) break; \
          if (el) { \
            fence_proxy_async_smem(); \
            mbar_expect_tx(bar_chk + c * 8, SLOT); \
            tma_load_2d(tile, c < 4 ? &tm_xb : &tm_o, bar_chk + c * 8, (c < 4 ? kslice(jj, c + 2) : wslice(jj, c + 5)) * 64, mm * 128); \
            RETRY_COUNT(); \
          } \
        } \
        if (el) mbar_arrive_local(bar_full + (c < 4 ? 4 + c : 37 + c) * 8); \
      }
#pragma unroll 1
      for (int l = 0; l < NLAYERS; l++) {
        int lane; asm volatile("mov.u32 %0, %%laneid;" : "=r"(lane));
        if (hw) CHECK_TILES(0, 4, X_BIT(l - 1), l == 0);
        {
          mbar_wait_sl(bar_done + 32, l & 1);
          const uint4* sp = reinterpret_cast<const uint4*>(g_stats + (size_t)(mm * 128 + hw * 64) * 8) + lane;
#pragma unroll 1
          for (int hf = 0; hf < 2; hf++) {
            uint4 v[4];
            uint32_t bad;
            int it = 0;
            do {
              bad = 0;
#pragma unroll
              for (int i = 0; i < 4; i++) { v[i] = ld_ll(sp + (hf * 4 + i) * 32); bad |= (v[i].y ^ STAT_TAG(l)) | (v[i].w ^ STAT_TAG(l)); }
              bad &= 3;
              if (bad) __nanosleep(200);
            } while (bad && ++it < (1 << 16));
            __syncwarp();
            float mean = 0.f, m2 = 0.f;
#pragma unroll
            for (int i = 0; i < 4; i++) {
              float a = __uint_as_float(v[i].x) + __uint_as_float(v[i].z);
              a += __shfl_xor_sync(0xffffffffu, a, 1); a += __shfl_xor_sync(0xffffffffu, a, 2);
              a *= 0.125f;
              const float e0 = __uint_as_float(v[i].x) - a, e1 = __uint_as_float(v[i].z) - a;
              float q = fmaf(fmaf(e0, e0, e1 * e1), 128.f, __uint_as_float(v[i].y) + __uint_as_float(v[i].w));
              q += __shfl_xor_sync(0xffffffffu, q, 1); q += __shfl_xor_sync(0xffffffffu, q, 2);
              if ((lane & 3) == i) { mean = a; m2 = q; }
            }
            const uint32_t row = hw * 64 + hf * 32 + (lane & 3) * 8 + (lane >> 2);
            uint32_t h, m, lo;
            split3(-0.5f * mean, h, m, lo);
            sts128(sbase + OFF_LNA + row * 16, h | (h << 16), m | (h << 16), lo | (m << 16), m | (lo << 16));
            sts32f(sbase + OFF_ST + row * 4, rsqrtf(m2 * (1.f / 1024.f) + 1e-5f));
          }
          fence_proxy_async_smem();
          __syncwarp();
          if (el && hw) mbar_arrive_local(bar_stat);
          const uint4* src = reinterpret_cast<const uint4*>(g_colsum[l & 1][jj * 64 + hw * 32 + lane]);
          uint32_t bad;
          int it = 0;
          float c[6];
          do {
            bad = 0;
#pragma unroll
            for (int p = 0; p < 3; p++) {
              const uint4 v = ld_ll(src + p * 512);
              bad |= (v.y ^ ep1) | (v.w ^ ep1);
              c[2 * p] = __uint_as_float(v.x) + __uint_as_float(v.z); c[2 * p + 1] = __uint_as_float(v.y) + __uint_as_float(v.w);
            }
            bad &= 3;
            if (bad) __nanosleep(300);
          } while (bad && ++it < (1 << 16));
#pragma unroll
          for (int p = 0; p < 6; p++) {
            uint32_t h, m, lo;
            split3(c[p], h, m, lo);
            sts128(sbase + OFF_LNB + hw * 4096 + (p >> 1) * 1024 + lane * 32 + (p & 1) * 16, h | (m << 16), h | (lo << 16), h | (m << 16), lo | (m << 16));
          }
          fence_proxy_async_smem();
          __syncwarp();
          if (el) { mbar_arrive_local(hw ? bar_stat2 : bar_stat); PROFT(323 + l * 16 + hw); }
        }
        if (hw) {
          if (l & 1) {
#pragma unroll 1
            for (int h = 0; h < 2; h++) {
              asm volatile("bar.sync %0, 288;" :: "r"(BAR_KV + h) : "memory");
              __syncwarp();
              PROFT(331 + l * 16 + h);
              if (lane < 16) signal_release(&g_flags.kvready[(l & 2) + h][jj][lane].v);
              const unsigned* kf = &g_flags.kvready[(l & 2) + h][jj][mm].v;
              unsigned v0 = ld_relaxed(kf);
              __nanosleep(150);
              unsigned v1 = ld_relaxed(kf);
#pragma unroll 1
              for (int it = 0; it < (1 << 18); it++) {
                if (v0 == ep1 * 16) break;
                v0 = ld_relaxed(kf);
                if (v1 == ep1 * 16) break;
                v1 = ld_relaxed(kf);
              }
              fence_acquire();
              __syncwarp();
              if (el) { mbar_arrive_local(bar_kvf + h * 8); PROFT(333 + l * 16 + h); }
            }
          } else if (l == 0 && NLAYERS > 1) {
#pragma unroll 1
            for (int ph = 0; ph < 3; ph++) {
              asm volatile("bar.sync %0, 288;" :: "r"(BAR_WF + ph + (ph > 0)) : "memory");
              if (el) {
                if (ph == 1) mbar_expect_tx(bar_phi + 8, SLOT);
#pragma unroll 1
                for (int i = 0; i < 4; i++) {
                  const uint32_t a = sbase + (ph ? 10 : 12) * SLOT + i * 4096;
                  const int c0 = (ph ? 1024 : 0) + jj * 128 + (i >> 1) * 64, c1 = mm * 64 + (i & 1) * 32;
                  if (ph == 1) tma_load_2d(a, &tm_wqB, bar_phi + 8, c0, c1); else tma_store_2d(&tm_wf, a, c0, c1);
                }
                if (ph != 1) {
                  asm volatile("cp.async.bulk.commit_group;\ncp.async.bulk.wait_group.read 0;" ::: "memory");
                  mbar_arrive_local(bar_phi + ph * 4);
                }
                if (ph == 2) {
                  asm volatile("cp.async.bulk.wait_group 0;" ::: "memory");
                  signal_release(&g_flags.wfready[jj].v);
                  PROFT(335);
                }
              }
              __syncwarp();
            }
          }
        }
        if (hw) { CHECK_TILES(4, 11, O_BIT(l), false); }
        else {
#pragma unroll 1
          for (int e = 0; e < 4; e++) {
            asm volatile("bar.sync %0, 288;" :: "r"(BAR_O + e) : "memory");
            if (el) {
              PROFT(325 + l * 16 + e);
              tma_store_2d((e & 2) ? (l < NLAYERS - 1 ? &tm_xb : &tm_xo) : &tm_o, sbase + ((0xBA3C >> (4 * e)) & 15) * SLOT, jj * 128 + (e & 1) * 64, mm * 128);
              if (e != 2) bulk_commit_wait();
              if (e & 1) PROFT(480 + l * 2 + (e >> 1));
              if (e == 1) { mbar_arrive_remote(bar_o1s, 0); mbar_arrive_remote(bar_o1s, 1); }
              else if (e == 0) signal_release(&g_flags.oready[l][mm].v);
              else if (e == 3 && l < NLAYERS - 1) signal_release(&g_flags.xready[l + 1][mm].v);
              if (e & 1) PROFT(329 + l * 16 + (e >> 1));
            }
            __syncwarp();
          }
        }
      }
    }
    cluster_sync();
  } else {
    asm volatile("setmaxnreg.inc.sync.aligned.u32 232;");
    const int wg = warp >> 2;
    const int r0 = warp * 16;
    const uint32_t pK = sbase + OFF_S, pV = sbase + OFF_S + SLOT;
#define PMASKS(on, bit) const uint32_t pm0 = ((on) && t == (g & 3) && (g >> 2) == (g & 1)), pm1 = ((on) && t == (g & 3) && (g >> 2) != (g & 1)), pbit = (bit)
#define PBIT0(w) (((w) & ~pm0) | (pbit & pm0))
#define PBIT1(w) (((w) & ~pm1) | (pbit & pm1))
#define LANE_CONSTS() \
    int lane; asm volatile("mov.u32 %0, %%laneid;" : "=r"(lane)); \
    const int g = lane >> 2, t = lane & 3; \
    const uint32_t srowoff = (r0 + (lane & 15)) * 128, lsw = (lane & 7) << 4, lhi = (lane >> 4) << 4, lsw2 = (lane & 6) << 3; \
    (void)g; (void)t; (void)srowoff; (void)lsw; (void)lhi; (void)lsw2;
    uint32_t stgp = 0;
    cluster_wait();
#define STG_ARRIVE() { __syncwarp(); if (elect_one()) mbar_arrive_local(bar_stg); }
#define STG_WAIT() { mbar_wait(bar_stg, stgp); stgp ^= 1; }
#define PROFS() do {} while (0)
#define REL(addr) { if (elect_one()) { mbar_arrive_remote(addr, 0); mbar_arrive_remote(addr, 1); } }
#define QSTEP(ACC, AADDR, SC, PRE) { \
      const uint64_t da = make_desc(AADDR, 16, 1024), db = make_desc(sbase + ((ub >> 3) & 3) * QST, 8192, 1024); \
      mbar_wait(ub, par); \
      PRE; \
      wgmma_fence(); \
      wgmma_n192<SC>(ACC, da, db); \
      _Pragma("unroll") for (int k4 = 1; k4 < 4; k4++) wgmma_n192<1>(ACC, da + k4 * 2, db + k4 * 128); \
      wgmma_commit(); PROFS(); }
#define QREL() { wgmma_wait<1>(); REL(ub + 376); ub += 8; }
#define RA_CUR (sbase + OFF_RA + ((ub << 11) & 0xC000) + wg * 8192)
#define PUMP0() { QSTEP(S1, RA_CUR, 1, {}); QREL(); SCHED_FENCE(); }
#define PUMP() if (h == 0) PUMP0()
#define PUMPC() { if (h == 0) PUMP0() else wgmma_wait<0>(); }
#define WSTEP() { \
      const uint32_t s4 = (ub - bar_full - 256) >> 1; \
      const uint64_t da = make_desc(sbase + (uint32_t)((WO_ASLOT(par) >> s4) & 15) * SLOT + wg * 8192, 16, 1024); \
      const uint64_t db = make_desc(sbase + (uint32_t)((WO_BSLOT >> s4) & 15) * SLOT, 8192, 1024); \
      mbar_wait(ub, par); \
      wgmma_fence(); \
      _Pragma("unroll") for (int k4 = 0; k4 < 4; k4++) wgmma_n128<1>(S1, da + k4 * 2, db + k4 * 128); \
      wgmma_commit(); PROFS(); \
      wgmma_wait<1>(); \
      if (s4 > par * 4) REL(ub + 376); \
      ub += 8; }
#define PUMPS(n) { _Pragma("unroll 1") for (int i_ = 0; i_ < (n); i_++) PUMP0(); }
#define SITE(n) { if (((BMASK >> (n)) & 1) && h == 0) PUMP0() else SCHED_FENCE(); }
#define LNSTEP(ACC, hh) { wgmma_fence(); wgmma_n192<1, 0>(ACC, make_desc(sbase + OFF_LNA + wg * 1024, 0, 128) ^ (1ull << 62), make_desc(sbase + OFF_LNB + (hh) * 4096, 0, 128) ^ (1ull << 62)); }
#define DRAIN_A(ACC, PMP) { \
      LANE_CONSTS(); \
      STAGE64(ACC, 64, pV, 1); \
      PMP; \
      STAGE64(ACC, 32, pK, 0); \
      STG_ARRIVE(); \
      _Pragma("unroll") for (int i_ = 0; i_ < 16; i_++) qa[i_] = pack_bf16(ACC[2 * i_], ACC[2 * i_ + 1]); \
      PINU(qa, 16); }
#define DRAIN_B(ACC) { \
      LANE_CONSTS(); \
      STAGE64(ACC, 64, pV, 1); \
      _Pragma("unroll") for (int i_ = 0; i_ < 64; i_++) st[i_] = ACC[i_]; \
      PIN(st, 64); }
#define PUBLISH_O() { fence_proxy_async_smem(); asm volatile("bar.arrive %0, 288;" :: "r"(BAR_O + h) : "memory"); }
#define REST_P1(SKEW) { \
      mbar_wait(bar_stat2, par); \
      LNSTEP(S1, 1); \
      _Pragma("unroll 1") while (ub < bar_full + 256) { \
        if (ub == bar_full + 256 - 8 * (SKEW) && wg == 0) bar_sync<BAR_SKEW, 256>(); \
        QSTEP(S1, RA_CUR, 1, {}); \
        if (ub == bar_full + 248 && wg == 1) bar_arrive<BAR_SKEW, 256>(); \
        QREL(); \
      } \
      hbase += 256; \
      mbar_wait(bar_done + (31 - (SKEW)) * 8, par);        \
      wgmma_wait<0>(); \
      ACC_FENCE(S1, 96); \
      REL(bar_done + 31 * 8); \
      PROF(13); }
#define KV_LOAD(v, hh) { \
          const float4* kvg_ = reinterpret_cast<const float4*>(g_kv[l >> 1] + (jj * 4 + (hh) * 2 + wg) * KVH) + (warp & 3) * 32 + lane; \
          mbar_wait(bar_kvf + (hh) * 8, l >> 1); \
          _Pragma("unroll") for (int i = 0; i < 5; i++) { const float4 q_ = __ldcg(kvg_ + i * 128); (v)[i * 4] = q_.x; (v)[i * 4 + 1] = q_.y; (v)[i * 4 + 2] = q_.z; (v)[i * 4 + 3] = q_.w; } }
#define KV_TILE(v, pT) { \
          const uint32_t kd = (pT) + wg * 8192 + ((warp & 3) * 16 + (lane & 15)) * 128; \
          _Pragma("unroll") for (int i = 0; i < 2; i++) \
            stsm_x4(kd + ((i * 32 + lhi) ^ lsw), pack_bf16((v)[i * 8], (v)[i * 8 + 1]), pack_bf16((v)[i * 8 + 2], (v)[i * 8 + 3]), pack_bf16((v)[i * 8 + 4], (v)[i * 8 + 5]), pack_bf16((v)[i * 8 + 6], (v)[i * 8 + 7])); \
          stsm_x4(kd + ((64u + lhi) ^ lsw), pack_bf16((v)[16], 1.f), pack_bf16((v)[18], 1.f), 0u, 0u); }
#define O_MMA(o, pA, pB, pT) { \
          _Pragma("unroll") for (int hh = 0; hh < 2; hh++) { \
            const uint64_t da = make_desc((hh ? (pB) : (pA)) + wg * 8192, 16, 1024), db = make_desc((pT) + hh * 8192, 16, 1024); \
            _Pragma("unroll") for (int ks = 0; ks < 4; ks += 2) { \
              wgmma_n40<0, 0>((o) + hh * 48 + ks * 12, da + ks * 2, db + ks * 128); wgmma_n40<1, 0>((o) + hh * 48 + ks * 12, da + ks * 2 + 2, db + ks * 128 + 128); } \
          } \
          wgmma_commit(); }
#define O_OUT(o, pA, hp) { \
          bar_wg(wg);            \
          PMASKS(hp, O_BIT(l)); \
          _Pragma("unroll") for (int hh = 0; hh < 2; hh++) { \
            const float* x = (o) + hh * 48; \
            const float* y = x + 24; \
            const float rx0 = rcp_fast(x[17]), ry0 = rcp_fast(y[17]), rx1 = rcp_fast(x[19]), ry1 = rcp_fast(y[19]); \
            const float i0 = rcp_fast(fmaf(x[16], rx0, y[16] * ry0) + 1e-6f), i1 = rcp_fast(fmaf(x[18], rx1, y[18] * ry1) + 1e-6f); \
            const float ax0 = rx0 * i0, ay0 = ry0 * i0, ax1 = rx1 * i1, ay1 = ry1 * i1; \
            _Pragma("unroll") for (int dp = 0; dp < 2; dp++) \
              stsm_x4((pA) + srowoff + ((hh * 64 + dp * 32 + lhi) ^ lsw), \
                      PBIT0(pack_bf16(fmaf(x[dp * 8], ax0, y[dp * 8] * ay0), fmaf(x[dp * 8 + 1], ax0, y[dp * 8 + 1] * ay0))), \
                      PBIT0(pack_bf16(fmaf(x[dp * 8 + 2], ax1, y[dp * 8 + 2] * ay1), fmaf(x[dp * 8 + 3], ax1, y[dp * 8 + 3] * ay1))), \
                      PBIT1(pack_bf16(fmaf(x[dp * 8 + 4], ax0, y[dp * 8 + 4] * ay0), fmaf(x[dp * 8 + 5], ax0, y[dp * 8 + 5] * ay0))), \
                      PBIT1(pack_bf16(fmaf(x[dp * 8 + 6], ax1, y[dp * 8 + 6] * ay1), fmaf(x[dp * 8 + 7], ax1, y[dp * 8 + 7] * ay1)))); \
          } \
          fence_proxy_async_smem(); \
          bar_arrive<BAR_O + (hp), 288>(); }
#define FOLD(tile, rd) { \
          LANE_CONSTS(); \
          float d[32]; \
          ACC_DEF(d, 32); \
          mbar_wait(bar_phi + (rd) * 8, 0); \
          wgmma_fence(); \
          _Pragma("unroll") for (int i = 0; i < 2; i++) { \
            const uint64_t da = make_desc((tile) + wg * 8192 + i * 64, 16, 1024); \
            const uint64_t db = make_desc(sbase + OFF_PHI + wg * 4096 + i * 2048, 16, 512) ^ (3ull << 62); \
            wgmma_n32<0>(d + i * 16, da, db); wgmma_n32<1>(d + i * 16, da + 2, db + 64); \
          } \
          wgmma_commit(); \
          PUMP0(); \
          ACC_FENCE(d, 32); \
          bar_wg(wg); \
          _Pragma("unroll") for (int i = 0; i < 4; i++) { \
            const float* x = d + (i & 1) * 8 + (i >> 1) * 2; \
            sts128((tile) + wg * 8192 + ((warp & 3) * 16 + (i >> 1) * 8 + g) * 128 + (((2 * t + (i & 1)) ^ g) << 4), \
                   pack_bf16(x[0], x[1]), pack_bf16(x[4], x[5]), pack_bf16(x[16], x[17]), pack_bf16(x[20], x[21])); \
          } \
          fence_proxy_async_smem(); \
          bar_arrive<BAR_WF + 3 * (rd), 288>(); }
#define LOAD_X0(base) \
      _Pragma("unroll") for (int j = 0; j < 8; j++) { \
        uint32_t x0, x1, x2, x3; \
        ldsm_x4((base) + (j >> 2) * SLOT + srowoff + ((((uint32_t)(j & 3) << 5) + lhi) ^ lsw), x0, x1, x2, x3); \
        S1[j * 8 + 0] = bf_lo(x0); S1[j * 8 + 1] = bf_hi(x0); S1[j * 8 + 2] = bf_lo(x1); S1[j * 8 + 3] = bf_hi(x1); \
        S1[j * 8 + 4] = bf_lo(x2); S1[j * 8 + 5] = bf_hi(x2); S1[j * 8 + 6] = bf_lo(x3); S1[j * 8 + 7] = bf_hi(x3); \
      }
#define LOAD_X() { \
      wgmma_wait<0>(); \
      mbar_wait(bar_xr, par); \
      LOAD_X0(sbase + OFF_RA); \
      ACC_FENCE(S1, 64); \
      __syncwarp(); if (elect_one()) mbar_arrive_local(bar_lx); }

    float S1[96];
#pragma unroll
    for (int i = 0; i < 64; i++) S1[i] = 0.f;
#pragma unroll 1
    for (int l = 0; l < NLAYERS; l++) {
      const uint32_t par = l & 1;
      bar_wg(wg);
      PROF(0);
      uint32_t ub = bar_full;
      const bool hsend = (warp == 7) && !par && (mm < 15);
      const uint32_t hbit = (NLAYERS > 2) ? (l == 0) : (ep1 & 1);
      float S0[96];
      {
        LANE_CONSTS();
        ACC_DEF(S0, 96);
        QSTEP(S0, pK + wg * 8192, 0, {});
        ub += 8;
        PROF(1);
        if (l == 0) { mbar_wait(ub, 0); LOAD_X0(pK); }
        SCHED_FENCE();
        {
          float a0 = 0.f, a1 = 0.f, b0 = 0.f, b1 = 0.f;
#pragma unroll
          for (int i = 0; i < 64; i += 4) { a0 += S1[i]; b0 += S1[i + 1]; a1 += S1[i + 2]; b1 += S1[i + 3]; }
          a0 += b0; a1 += b1;
          a0 += __shfl_xor_sync(0xffffffffu, a0, 1); a1 += __shfl_xor_sync(0xffffffffu, a1, 1);
          a0 += __shfl_xor_sync(0xffffffffu, a0, 2); a1 += __shfl_xor_sync(0xffffffffu, a1, 2);
          a0 *= (1.f / 128.f); a1 *= (1.f / 128.f);
          asm volatile("" : "+f"(a0), "+f"(a1));
          QSTEP(S0, pV + wg * 8192, 1, wgmma_wait<0>());
          REL(ub + 376); ub += 8;
          SCHED_FENCE();
          float q0 = 0.f, q1 = 0.f;
          b0 = 0.f; b1 = 0.f;
#pragma unroll
          for (int i = 0; i < 64; i += 4) {
            const float d0 = S1[i] - a0, d1 = S1[i + 1] - a0, d2 = S1[i + 2] - a1, d3 = S1[i + 3] - a1;
            q0 = fmaf(d0, d0, q0); b0 = fmaf(d1, d1, b0); q1 = fmaf(d2, d2, q1); b1 = fmaf(d3, d3, b1);
          }
          q0 += b0; q1 += b1;
          q0 += __shfl_xor_sync(0xffffffffu, q0, 1); q1 += __shfl_xor_sync(0xffffffffu, q1, 1);
          q0 += __shfl_xor_sync(0xffffffffu, q0, 2); q1 += __shfl_xor_sync(0xffffffffu, q1, 2);
          if (t < 2) st_b64(g_stats + (size_t)(mm * 128 + r0 + g + t * 8) * 8 + jj, __float_as_uint(t ? a1 : a0), (__float_as_uint(t ? q1 : q0) & ~3u) | STAT_TAG(l));
        }
        ACC_DEF(S1, 96);
        QSTEP(S1, pK + wg * 8192, 0, {});
        QREL();
        QSTEP(S1, pV + wg * 8192, 1, {});
        QREL();
#pragma unroll 1
        for (int i = 0; i < 14; i++) {
          QSTEP(S0, RA_CUR, 1, {});
          if (i == 0) PROF(2);
          QREL();
        }
      }
      LANE_CONSTS();
      uint4* hbase = g_halo + (size_t)(mm * 8 + jj) * 512;
      mbar_wait(bar_stat, par);
      LNSTEP(S0, 0);
      wgmma_commit();
      const float rs0 = lds32f(sbase + OFF_ST + (r0 + g) * 4), rs1 = lds32f(sbase + OFF_ST + (r0 + g + 8) * 4);
      PUMP0();
      ACC_FENCE(S0, 96);
      PROF(3);
      if (!par) {
        uint32_t qa[16];
        DRAIN_A(S0, PUMP0());
#pragma unroll 1
        for (int h = 0; h < 2; h++) {
          const uint32_t pO = sbase + (h ? 3 : 12) * SLOT;
          PROF(4 + h * 12);
          const bool fold = (l == 0 && h == 0 && NLAYERS > 1);
          if (fold) FOLD(pO, 0) else if (h == 0) PUMPS(HPUMP1);
          LANE_CONSTS();
          uint4 hv[8];
#pragma unroll
          for (int i = 0; i < 8; i++) hv[i] = make_uint4(hbit, 0, 0, 0);
          const bool hrec = (warp == 0 && mm > 0);
          if (hrec) {
#pragma unroll
            for (int i = 0; i < 8; i++) hv[i] = ld_b128(hbase + lane - 8 * 512 + i * 32);
          }
          if (h) LOAD_X() else PUMPS(HPUMP2);
          const uint32_t halo = sbase + OFF_HALO;
          STG_WAIT();
          if (warp == 0) {
#pragma unroll 1
            for (int it = 0; it < (1 << 16); it++) {
              uint32_t bad = 0;
#pragma unroll
              for (int i = 0; i < 8; i++) bad |= hv[i].x ^ hbit;
              if (__all_sync(0xffffffffu, (bad & 1) == 0)) break;
#pragma unroll
              for (int i = 0; i < 8; i++) hv[i] = ld_b128(hbase + lane - 8 * 512 + i * 32);
            }
#pragma unroll
            for (int i = 0; i < 8; i++)
              stsm_x4(i < 4 ? halo + srowoff + ((((uint32_t)i << 5) + lhi) ^ lsw)
                            : halo + (srowoff >> 1) + (i >> 1) * 1024 + ((((uint32_t)(i & 1) << 5) + lhi) ^ lsw2), hv[i].x, hv[i].y, hv[i].z, hv[i].w);
            __syncwarp();
          }
          PROF(5 + h * 12);
          const uint32_t kb1 = pK + r0 * 128, vb1 = pV + r0 * 64;
          const uint32_t kb0 = r0 ? kb1 - 2048 : halo, vb0 = r0 ? vb1 - 1024 : halo + 2048;
          const uint32_t vhs = r0 ? 8192 : 1024;
          float s[2][4][4];
          {
            uint32_t kf[2][4][4];
#pragma unroll
            for (int i = 0; i < 8; i++) {
              const int hh = i >> 2, jb = i & 3;
              ldsm_x4(((jb < 2) ? kb0 : kb1) + ((jb & 1) * 8 + (lane & 7)) * 128 + ((hh * 64 + ((lane >> 3) << 4)) ^ lsw), kf[hh][jb][0], kf[hh][jb][1], kf[hh][jb][2], kf[hh][jb][3]);
              s[hh][jb][0] = s[hh][jb][1] = s[hh][jb][2] = s[hh][jb][3] = 0.f;
            }
#pragma unroll
            for (int ks = 0; ks < 2; ks++)
#pragma unroll
              for (int i = 0; i < 8; i++) {
                const int hh = i >> 2, jb = i & 3;
                mma_bf16(s[hh][jb], qa[hh * 8 + ks * 4], qa[hh * 8 + ks * 4 + 1], qa[hh * 8 + ks * 4 + 2], qa[hh * 8 + ks * 4 + 3], kf[hh][jb][ks * 2], kf[hh][jb][ks * 2 + 1]);
              }
          }
          PUMP();
          if (fold) bar_arrive<BAR_WF + 2, 288>();
          PROF(6 + h * 12);
          const bool e = g & 1, hb = (2 * t + (g & 1)) <= g;
          uint32_t vf[2][2][2][4];
#pragma unroll
          for (int i = 0; i < 8; i++) {
            const int hh = i >> 2, ks = (i >> 1) & 1, dp = i & 1;
            ldsm_x4_t((ks ? vb1 + hh * 8192 : vb0 + hh * vhs) + (lane & 15) * 64 + ((dp * 32 + lhi) ^ lsw2), vf[hh][ks][dp][0], vf[hh][ks][dp][1], vf[hh][ks][dp][2], vf[hh][ks][dp][3]);
          }
          float va[2][2], vb[2][2], mx[2][2];
#pragma unroll
          for (int hh = 0; hh < 2; hh++) {
            va[hh][0] = e ? s[hh][1][1] : s[hh][1][0];
            vb[hh][0] = hb ? (e ? s[hh][2][1] : s[hh][2][0]) : (e ? s[hh][0][1] : s[hh][0][0]);
            va[hh][1] = e ? s[hh][2][3] : s[hh][2][2];
            vb[hh][1] = hb ? (e ? s[hh][3][3] : s[hh][3][2]) : (e ? s[hh][1][3] : s[hh][1][2]);
          }
          if (warp == 0 && mm == 0) {
#pragma unroll
            for (int hh = 0; hh < 2; hh++) { va[hh][0] = -INFINITY; if (!hb) { vb[hh][0] = -INFINITY; vb[hh][1] = -INFINITY; } }
          }
#pragma unroll
          for (int i = 0; i < 4; i++) mx[i >> 1][i & 1] = fmaxf(va[i >> 1][i & 1], vb[i >> 1][i & 1]);
#pragma unroll
          for (int o = 1; o <= 2; o <<= 1)
#pragma unroll
            for (int i = 0; i < 4; i++) mx[i >> 1][i & 1] = fmaxf(mx[i >> 1][i & 1], __shfl_xor_sync(0xffffffffu, mx[i >> 1][i & 1], o));
          const float sc0 = rs0 * (0.17677669529663687f * LOG2E), sc1 = rs1 * (0.17677669529663687f * LOG2E);
#pragma unroll
          for (int i = 0; i < 4; i++) {
            const float sc = (i & 1) ? sc1 : sc0, m = mx[i >> 1][i & 1];
            va[i >> 1][i & 1] = ex2((va[i >> 1][i & 1] - m) * sc); vb[i >> 1][i & 1] = ex2((vb[i >> 1][i & 1] - m) * sc);
            mx[i >> 1][i & 1] = va[i >> 1][i & 1] + vb[i >> 1][i & 1];
          }
          if (h == 0 && ASITE) { PIN(&va[0][0], 4); PIN(&vb[0][0], 4); PIN(&mx[0][0], 4); PUMP0(); }
#pragma unroll
          for (int o = 1; o <= 2; o <<= 1)
#pragma unroll
            for (int i = 0; i < 4; i++) mx[i >> 1][i & 1] += __shfl_xor_sync(0xffffffffu, mx[i >> 1][i & 1], o);
          const uint32_t selA = e ? 0x1044 : 0x4410, selB = e ? 0x3244 : 0x4432, selL = hb ? 0x4444 : selB, selH = hb ? selB : 0x4444;
          float o[2][4][4];
          uint32_t pa[2][6];
#pragma unroll
          for (int hh = 0; hh < 2; hh++) {
            const float i0 = rcp_fast(mx[hh][0]), i1 = rcp_fast(mx[hh][1]);
            const uint32_t w0 = pack_bf16(va[hh][0] * i0, vb[hh][0] * i0), w1 = pack_bf16(va[hh][1] * i1, vb[hh][1] * i1);
            pa[hh][0] = __byte_perm(w0, 0, selL); pa[hh][1] = __byte_perm(w0, 0, selA); pa[hh][2] = __byte_perm(w1, 0, selL);
            pa[hh][3] = __byte_perm(w0, 0, selH); pa[hh][4] = __byte_perm(w1, 0, selA); pa[hh][5] = __byte_perm(w1, 0, selH);
#pragma unroll
            for (int dj = 0; dj < 4; dj++) { o[hh][dj][0] = o[hh][dj][1] = o[hh][dj][2] = o[hh][dj][3] = 0.f; }
          }
          PROF(7 + h * 12);
#pragma unroll
          for (int i = 0; i < 8; i++) mma_bf16(o[i >> 2][i & 3], pa[i >> 2][0], 0u, pa[i >> 2][1], pa[i >> 2][2], vf[i >> 2][0][(i >> 1) & 1][(i & 1) * 2], vf[i >> 2][0][(i >> 1) & 1][(i & 1) * 2 + 1]);
#pragma unroll
          for (int i = 0; i < 8; i++) mma_bf16(o[i >> 2][i & 3], pa[i >> 2][3], pa[i >> 2][4], 0u, pa[i >> 2][5], vf[i >> 2][1][(i >> 1) & 1][(i & 1) * 2], vf[i >> 2][1][(i >> 1) & 1][(i & 1) * 2 + 1]);
          if (h == 0) PUMP0() else mbar_wait(bar_done + 30 * 8, par);
          if (fold) mbar_wait(bar_phi, 1);
#pragma unroll
          for (int i = 0; i < 4; i++) {
            const int hh = i >> 1, dp = i & 1;
            PMASKS(h, O_BIT(l));
            stsm_x4(pO + srowoff + ((hh * 64 + dp * 32 + lhi) ^ lsw), PBIT0(pack_bf16(o[hh][dp * 2][0], o[hh][dp * 2][1])), PBIT0(pack_bf16(o[hh][dp * 2][2], o[hh][dp * 2][3])),
                    PBIT1(pack_bf16(o[hh][dp * 2 + 1][0], o[hh][dp * 2 + 1][1])), PBIT1(pack_bf16(o[hh][dp * 2 + 1][2], o[hh][dp * 2 + 1][3])));
          }
          PUBLISH_O();
          PROF(11 + h * 12);
          if (h) break;
          if (fold) { PUMPS(FPUMP); FOLD(pK, 1); }
          REST_P1(ASKEW);
          if (fold) mbar_wait(bar_phi + 8, 1);
          DRAIN_A(S1, {});
        }
      } else {
        float st[64];
        DRAIN_B(S0);
        if (warp < 2) sts128(sbase + OFF_ONES + warp * 512 + lane * 16, 0x3F803F80u, 0x3F803F80u, 0x3F803F80u, 0x3F803F80u);
        const float c0 = rs0 * LOG2E, c1 = rs1 * LOG2E;
#pragma unroll 1
        for (int h = 0; h < 2; h++) {
          const uint32_t pO = sbase + (h ? 3 : 12) * SLOT, pP = sbase + (h ? 9 : 10) * SLOT;
          PROF(4 + h * 12);
          SITE(0);
          LANE_CONSTS();
          const uint32_t dsw = (uint32_t)(g ^ (2 * t)) << 4;
          const float* pk = st + 32;
          float4* kvg = reinterpret_cast<float4*>(g_kv[l >> 1] + (jj * 4 + h * 2 + wg) * KVH) + (warp & 3) * 32 + lane;
          const uint32_t dst = ((t & 2) ? pP : pO) + (r0 + g) * 128;
          float mq[4];
          {
            float e[16], f[16];
            float mn0 = rmin16(pk);
            asm volatile("" : "+f"(mn0)); SCHED_FENCE();
            float sa = exps16(e, pk, -c0, mn0 * c0), mx0 = rmax16(pk);
            asm volatile("" : "+f"(sa), "+f"(mx0)); PIN(e, 16); SITE(1);
            store16(e, sa, dst, dsw, 4);
            float sb = exps16(f, pk, c0, -mx0 * c0), mn1 = rmin16(pk + 2);
            asm volatile("" : "+f"(sb), "+f"(mn1)); PIN(f, 16); SITE(2);
            float kv0[20];
#pragma unroll
            for (int i = 0; i < 20; i++) kv0[i] = 0.f;
            if (h) KV_LOAD(kv0, 0);
            store16(f, sb, dst, dsw, 0);
            float sc = exps16(e, pk + 2, -c1, mn1 * c1), mx1 = rmax16(pk + 2);
            asm volatile("" : "+f"(sc), "+f"(mx1)); PIN(e, 16); SITE(3);
            store16(e, sc, dst + 1024, dsw, 4);
            float sd = exps16(f, pk + 2, c1, -mx1 * c1);
            asm volatile("" : "+f"(sd)); PIN(f, 16); SITE(4);
            store16(f, sd, dst + 1024, dsw, 0);
            if (h) KV_TILE(kv0, sbase + 8 * SLOT);
          }
          fence_proxy_async_smem();
          STG_ARRIVE();
          PROF(5 + h * 12);
          uint32_t fq[32];
          {
            const uint64_t dp = make_desc(wg ? pP : pO, 16, 1024);
            const uint64_t dv = (make_desc(pV + wg * 8192, OFF_ONES - OFF_S - SLOT - wg * 8192, 512) ^ (3ull << 62));
            constexpr uint64_t DVS = 64ull - (64ull << 16);
            mq[0] = rmin16(st);
            asm volatile("" : "+f"(mq[0])); SITE(5);
            STG_WAIT();
            PROF(8 + h * 12);
#define KV_MMA() \
              float kv[20]; \
              ACC_DEF(kv, 20); \
              wgmma_fence(); \
              _Pragma("unroll") for (int ks = 0; ks < 8; ks++) { if (ks == 0) wgmma_n40<0, 1>(kv, dp, dv); else wgmma_n40<1, 1>(kv, dp + ks * 128, dv + ks * DVS); } \
              wgmma_commit();
#define KV_OUT(...) { \
              SCHED_FENCE(); \
              mq[1] = rmax16(st); mq[2] = rmin16(st + 2); mq[3] = rmax16(st + 2); \
              asm volatile("" : "+f"(mq[1]), "+f"(mq[2]), "+f"(mq[3])); \
              PROF(9 + h * 12); \
              __VA_ARGS__; \
              PROF(10 + h * 12); \
              ACC_FENCE(kv, 20); \
              _Pragma("unroll") for (int i = 0; i < 5; i++) red_v4(reinterpret_cast<float*>(kvg + i * 128), kv[i * 4], kv[i * 4 + 1], kv[i * 4 + 2], kv[i * 4 + 3]); \
              asm volatile("bar.arrive %0, 288;" :: "r"(BAR_KV + h) : "memory"); \
              STG_ARRIVE(); \
              PROF(6 + h * 12); }
            if (h == 0) { KV_MMA(); KV_OUT(PUMP0()); } else {
              float o[96];
              wgmma_wait<0>();
              ACC_DEF(o, 96);
              KV_MMA();
              KV_OUT({ wgmma_fence(); O_MMA(o, sbase + 12 * SLOT, sbase + 10 * SLOT, sbase + 8 * SLOT); wgmma_wait<1>(); });
              wgmma_wait<0>();
              ACC_FENCE(o, 20); ACC_FENCE((o + 24), 20); ACC_FENCE((o + 48), 20); ACC_FENCE((o + 72), 20);
              O_OUT(o, sbase + 12 * SLOT, 0);
              PROF(26);
              LOAD_X();
            }
          }
          expp16(fq, st, -c0, mq[0] * c0);
          PINU(fq, 8); SITE(6);
          expp16(fq + 8, st, c0, -mq[1] * c0);
          PINU(fq + 8, 8); SITE(7);
          STG_WAIT();
#pragma unroll
          for (int i = 0; i < 4; i++) sts128(dst + (((((i & 2) ? 0 : 4) + (i & 1)) << 4) ^ dsw), fq[i * 4], fq[i * 4 + 1], fq[i * 4 + 2], fq[i * 4 + 3]);
          expp16(fq + 16, st + 2, -c1, mq[2] * c1);
          PINU(fq + 16, 8); SITE(8);
          expp16(fq + 24, st + 2, c1, -mq[3] * c1);
#pragma unroll
          for (int i = 4; i < 8; i++) sts128(dst + 1024 + (((((i & 2) ? 0 : 4) + (i & 1)) << 4) ^ dsw), fq[i * 4], fq[i * 4 + 1], fq[i * 4 + 2], fq[i * 4 + 3]);
          PROF(7 + h * 12);
          if (h) break;
          REST_P1(1);
          DRAIN_B(S1);
        }
        {
          LANE_CONSTS();
          bar_wg(wg);
          WSTEP();
          wgmma_wait<0>();
          REL(bar_done + 32 * 8);
          float o[96];
          KV_LOAD(o, 1);
          PROF(32);
          KV_TILE(o, pV);
          fence_proxy_async_smem();
          STG_ARRIVE();
          ACC_DEF(o, 96);
          STG_WAIT();
          PROF(33);
          wgmma_fence();
          O_MMA(o, sbase + 3 * SLOT, sbase + 9 * SLOT, pV);
          wgmma_wait<0>();
          ACC_FENCE(o, 20); ACC_FENCE((o + 24), 20); ACC_FENCE((o + 48), 20); ACC_FENCE((o + 72), 20);
          O_OUT(o, sbase + 3 * SLOT, 1);
          PROF(34);
        }
      }
      __syncwarp();
      if (elect_one()) mbar_arrive_local(bar_epi);
      bar_wg(wg);
#pragma unroll 1
      while (ub < bar_full + 384) {
        WSTEP();
        if (ub == bar_full + 8 * 41) PROF(35);
        if (ub == bar_full + 8 * 42) PROF(36);
      }
      wgmma_wait<0>();
      ACC_FENCE(S1, 64);
      REL(bar_done + 47 * 8);
      PROF(37);
      {
      LANE_CONSTS();
#pragma unroll
      for (int j = 0; j < 8; j++) {
        PMASKS(l < NLAYERS - 1 && j < 4, X_BIT(l));
        stsm_x4(pK + (j >> 2) * SLOT + srowoff + ((((uint32_t)(j & 3) << 5) + lhi) ^ lsw),
                PBIT0(pack_bf16(S1[j * 8 + 0], S1[j * 8 + 1])), PBIT0(pack_bf16(S1[j * 8 + 2], S1[j * 8 + 3])),
                PBIT1(pack_bf16(S1[j * 8 + 4], S1[j * 8 + 5])), PBIT1(pack_bf16(S1[j * 8 + 6], S1[j * 8 + 7])));
        if (j == 3) { fence_proxy_async_smem(); bar_arrive<BAR_O + 2, 288>(); }
      }
      }
      fence_proxy_async_smem();
      bar_arrive<BAR_O + 3, 288>();
      PROF(38);
    }
    const int tid = threadIdx.x;
    if (tid == 0) {
      unsigned old = atomicAdd(&g_flags.done.v, 1);
      if (old == ep1 * NMAIN - 1) {
        asm volatile("st.relaxed.gpu.global.u32 [%0], %1;" :: "l"(&g_flags.epoch.v), "r"(ep1) : "memory");
      }
    }
    __syncwarp();
    cluster_sync();
  }
}

typedef CUresult (*PFN_encode)(CUtensorMap*, CUtensorMapDataType, cuuint32_t, void*, const cuuint64_t*, const cuuint64_t*,
                               const cuuint32_t*, const cuuint32_t*, CUtensorMapInterleave, CUtensorMapSwizzle,
                               CUtensorMapL2promotion, CUtensorMapFloatOOBfill);

CUtensorMap make_map(PFN_encode enc, const void* ptr, uint64_t inner, uint64_t outer, uint32_t box_inner, uint32_t box_outer,
                     CUtensorMapSwizzle swz = CU_TENSOR_MAP_SWIZZLE_128B) {
  CUtensorMap m;
  cuuint64_t dims[2] = {inner, outer};
  cuuint64_t strides[1] = {inner * 2};
  cuuint32_t box[2] = {box_inner, box_outer};
  cuuint32_t es[2] = {1, 1};
  enc(&m, CU_TENSOR_MAP_DATA_TYPE_BFLOAT16, 2, const_cast<void*>(ptr), dims, strides, box, es, CU_TENSOR_MAP_INTERLEAVE_NONE,
      swz, CU_TENSOR_MAP_L2_PROMOTION_L2_256B, CU_TENSOR_MAP_FLOAT_OOB_FILL_NONE);
  return m;
}

}

extern "C" void kernel_launch(void* const* d_in, const int* in_sizes, int n_in, void* d_out, int out_size) {
  (void)in_sizes; (void)n_in; (void)out_size;
  static PFN_encode enc = nullptr;
  if (!enc) {
    void* fn = nullptr;
    cudaDriverEntryPointQueryResult qr;
    cudaGetDriverEntryPoint("cuTensorMapEncodeTiled", &fn, cudaEnableDefault, &qr);
    enc = (PFN_encode)fn;
    cudaFuncSetAttribute(mega_kernel, cudaFuncAttributeMaxDynamicSharedMemorySize, SMEM_BYTES);
  }
  Params prm;
  prm.x0 = (const __nv_bfloat16*)d_in[0];
  prm.wA_qkv = (const __nv_bfloat16*)d_in[1];
  prm.wA_o = (const __nv_bfloat16*)d_in[2];
  prm.wB_qkv = (const __nv_bfloat16*)d_in[4];
  prm.wB_phi = (const __nv_bfloat16*)d_in[5];
  prm.wB_o = (const __nv_bfloat16*)d_in[6];
  prm.out = (__nv_bfloat16*)d_out;
  void *obuf = nullptr, *xbuf = nullptr, *wf = nullptr;
  cudaGetSymbolAddress(&obuf, g_obuf);
  cudaGetSymbolAddress(&xbuf, g_xbuf);
  cudaGetSymbolAddress(&wf, g_wfold);
  CUtensorMap tm_x0 = make_map(enc, d_in[0], D_MODEL, S_LEN, 64, 128);
  CUtensorMap tm_xo = make_map(enc, d_out, D_MODEL, S_LEN, 64, 128);
  CUtensorMap tm_xb = make_map(enc, xbuf, D_MODEL, S_LEN, 64, 128);
  CUtensorMap tm_o = make_map(enc, obuf, D_MODEL, S_LEN, 64, 128);
  CUtensorMap tm_wf = make_map(enc, wf, 2048, D_MODEL, 64, 32);
  CUtensorMap tm_wqA = make_map(enc, d_in[1], 3 * D_MODEL, D_MODEL, 64, 32);
  CUtensorMap tm_wqB = make_map(enc, prm.wB_qkv, 3 * D_MODEL, D_MODEL, 64, 32);
  CUtensorMap tm_woA = make_map(enc, prm.wA_o, D_MODEL, D_MODEL, 64, 64);
  CUtensorMap tm_woB = make_map(enc, prm.wB_o, D_MODEL, D_MODEL, 64, 64);
  CUtensorMap tm_phi = make_map(enc, prm.wB_phi, 32, 1024, 32, 128, CU_TENSOR_MAP_SWIZZLE_64B);
  mega_kernel<<<NMAIN + NAUX, 384, SMEM_BYTES>>>(tm_x0, tm_xo, tm_xb, tm_o, tm_wf, tm_wqA, tm_wqB, tm_woA, tm_woB, tm_phi, prm);
}
```

```cpp
#include <cuda_runtime.h>
#include <cuda.h>
#include <cuda_bf16.h>
#include <stdint.h>

#define NLAYERS 4

#define STAG1 300
#define HPUMP1 2
#define HPUMP2 2
#define ASKEW 2
#define FPUMP 3
#define BMASK 0x1FF
#define ASITE 1
namespace {

constexpr int S_LEN = 2048, D_MODEL = 1024;
constexpr int NAUX = 4, NMAIN = 128;
constexpr int SLOT = 16384;
constexpr int QST = 24576;
constexpr int OFF_RA = 6 * SLOT, OFF_S = 10 * SLOT;
constexpr int OFF_HALO = 13 * SLOT, OFF_LNB = OFF_HALO  , OFF_ONES = OFF_HALO + 3072;
constexpr int OFF_ST = OFF_HALO + 7168  , OFF_PHI = OFF_HALO + 8192;
constexpr int OFF_BAR = 14 * SLOT;
constexpr int OFF_LNA = OFF_BAR + 1024;
constexpr int SMEM_BYTES = OFF_LNA + 2048;
#define WO_ASLOT(par) ((par) ? 0x689C7BA3689C768Cull : 0x68C97BA368C9768Cull)
constexpr unsigned long long WO_BSLOT = 0x5432105421054210ull;
__device__ __forceinline__ int kslice(int j, int i) { return i < 2 ? 2 * j + i : (i < 9 ? 2 * ((j + i - 1) & 7) : 2 * ((j + i) & 7) + 1); }
__device__ __forceinline__ int wslice(int j, int s) { return 2 * ((j + s) & 7) + (s >> 3); }
constexpr int KVH = 5 * 128 * 4;

struct __align__(128) Flag { unsigned v; unsigned pad[31]; };
struct Flags {
  Flag xready[4][16];
  Flag oready[4][16];
  Flag kvready[4][8][16];
  Flag wfready[8];
  Flag done;
  Flag epoch;
};

__device__ Flags g_flags;
__device__ __nv_bfloat16 g_obuf[S_LEN * D_MODEL];
__device__ __nv_bfloat16 g_xbuf[S_LEN * D_MODEL];
#define O_BIT(l) ((epoch * NLAYERS + (l) + 1) & 1u)
#define X_BIT(l) ((epoch * (NLAYERS - 1) + (l) + 1) & 1u)
__device__ __nv_bfloat16 g_wfold[D_MODEL * 2048];
__device__ uint4 g_halo[16 * 8 * 512];
__device__ float g_kv[2][32 * KVH];
__device__ __align__(128) uint2 g_colsum[2][1536][2];
__device__ __align__(128) uint2 g_stats[S_LEN * 8];
#define STAT_TAG(l) ((ep1 * NLAYERS + (l) + 1) & 3u)

#define RETRY_COUNT()
#define PROFL 1
#define PROFW 0
#define KVFLAG 1
#define PROFT(i) do {} while (0)
#define PROF(i) do {} while (0)

__device__ __forceinline__ uint32_t smem_u32(const void* p) { return (uint32_t)__cvta_generic_to_shared(p); }
__device__ __forceinline__ bool elect_one() {
  uint32_t p;
  asm volatile("{\n.reg .pred p;\nelect.sync _|p, 0xffffffff;\nselp.u32 %0, 1, 0, p;\n}\n" : "=r"(p));
  return p != 0;
}
__device__ __forceinline__ void mbar_init(uint32_t bar, uint32_t cnt) {
  asm volatile("mbarrier.init.shared::cta.b64 [%0], %1;" :: "r"(bar), "r"(cnt));
}
__device__ __forceinline__ void mbar_expect_tx(uint32_t bar, uint32_t bytes) {
  asm volatile("mbarrier.arrive.expect_tx.shared::cta.b64 _, [%0], %1;" :: "r"(bar), "r"(bytes) : "memory");
}
#define mbar_wait(bar, parity) \
  asm volatile("{\n.reg .pred p, q;\nW_%=:\nmbarrier.try_wait.parity.shared::cta.b64 p, [%1], %2;\nadd.s32 %0, %0, -1;\n" \
               "setp.gt.and.s32 q, %0, 0, !p;\n@q bra W_%=;\n}\n" : "+r"(budget) : "r"((uint32_t)(bar)), "r"((uint32_t)(parity)) : "memory")
#define mbar_wait_sl(bar, parity) \
  asm volatile("{\n.reg .pred p, q;\nW_%=:\nmbarrier.try_wait.parity.shared::cta.b64 p, [%1], %2, 20000;\nadd.s32 %0, %0, -64;\n" \
               "setp.gt.and.s32 q, %0, 0, !p;\n@q bra W_%=;\n}\n" : "+r"(budget) : "r"((uint32_t)(bar)), "r"((uint32_t)(parity)) : "memory")
__device__ __forceinline__ void mbar_arrive_local(uint32_t bar) {
  asm volatile("mbarrier.arrive.shared::cta.b64 _, [%0];" :: "r"(bar) : "memory");
}
__device__ __forceinline__ void mbar_arrive_remote(uint32_t bar, uint32_t cta_rank) {
  asm volatile("{\n.reg .b32 ra;\nmapa.shared::cluster.u32 ra, %0, %1;\nmbarrier.arrive.shared::cluster.b64 _, [ra];\n}\n"
               :: "r"(bar), "r"(cta_rank) : "memory");
}
__device__ __forceinline__ void tma_load_2d(uint32_t dst, const CUtensorMap* tm, uint32_t bar, int c0, int c1) {
  asm volatile("cp.async.bulk.tensor.2d.shared::cluster.global.mbarrier::complete_tx::bytes [%0], [%1, {%3, %4}], [%2];"
               :: "r"(dst), "l"(tm), "r"(bar), "r"(c0), "r"(c1) : "memory");
}
__device__ __forceinline__ void tma_load_2d_mc(uint32_t dst, const CUtensorMap* tm, uint32_t bar, int c0, int c1) {
  asm volatile("cp.async.bulk.tensor.2d.shared::cluster.global.mbarrier::complete_tx::bytes.multicast::cluster [%0], [%1, {%3, %4}], [%2], %5;"
               :: "r"(dst), "l"(tm), "r"(bar), "r"(c0), "r"(c1), "h"((uint16_t)3) : "memory");
}
__device__ __forceinline__ void tma_store_2d(const CUtensorMap* tm, uint32_t src, int c0, int c1) {
  asm volatile("cp.async.bulk.tensor.2d.global.shared::cta.bulk_group [%0, {%2, %3}], [%1];"
               :: "l"(tm), "r"(src), "r"(c0), "r"(c1) : "memory");
}
__device__ __forceinline__ void bulk_commit_wait() {
  asm volatile("cp.async.bulk.commit_group;\ncp.async.bulk.wait_group 0;" ::: "memory");
}
__device__ __forceinline__ void prefetch_l2(const void* p, uint32_t bytes) {
  asm volatile("cp.async.bulk.prefetch.L2.global [%0], %1;" :: "l"(p), "r"(bytes) : "memory");
}
__device__ __forceinline__ void prefetch_tmap(const CUtensorMap* tm) {
  asm volatile("prefetch.tensormap [%0];" :: "l"(tm) : "memory");
}
__device__ __forceinline__ void fence_proxy_async_global() { asm volatile("fence.proxy.async.global;" ::: "memory"); }
__device__ __forceinline__ void fence_proxy_async_smem() { asm volatile("fence.proxy.async.shared::cta;" ::: "memory"); }
__device__ __forceinline__ unsigned ld_relaxed(const unsigned* p) {
  unsigned v;
  asm volatile("ld.relaxed.gpu.global.u32 %0, [%1];" : "=r"(v) : "l"(p) : "memory");
  return v;
}
__device__ __forceinline__ void fence_acquire() { asm volatile("fence.acquire.gpu;" ::: "memory"); }
__device__ __forceinline__ void wait_flag(const unsigned* p, unsigned target) {
  int it = 0;
  while ((int)(ld_relaxed(p) - target) < 0 && ++it < (1 << 20)) {}
  fence_acquire();
}
__device__ __forceinline__ void signal_release(unsigned* p) {
  asm volatile("red.release.gpu.global.add.u32 [%0], 1;" :: "l"(p) : "memory");
}
template <int ID, int N> __device__ __forceinline__ void bar_arrive() { asm volatile("bar.arrive %0, %1;" :: "n"(ID), "n"(N) : "memory"); }
template <int ID, int N> __device__ __forceinline__ void bar_sync() { asm volatile("bar.sync %0, %1;" :: "n"(ID), "n"(N) : "memory"); }
__device__ __forceinline__ void bar_wg(int wg) { asm volatile("bar.sync %0, 128;" :: "r"(2 + wg) : "memory"); }
__device__ __forceinline__ void cluster_sync() {
  asm volatile("barrier.cluster.arrive.relaxed.aligned;\nbarrier.cluster.wait.aligned;" ::: "memory");
}
__device__ __forceinline__ void cluster_wait() { asm volatile("barrier.cluster.wait.acquire.aligned;" ::: "memory"); }
enum { BAR_KV = 4  , BAR_O = 7  , BAR_WF = 12  , BAR_SKEW = 13 };

__device__ __forceinline__ void wgmma_fence() { asm volatile("wgmma.fence.sync.aligned;" ::: "memory"); }
__device__ __forceinline__ void wgmma_commit() { asm volatile("wgmma.commit_group.sync.aligned;" ::: "memory"); }
template <int N> __device__ __forceinline__ void wgmma_wait() { asm volatile("wgmma.wait_group.sync.aligned %0;" :: "n"(N) : "memory"); }

template <int scale_d, int tnsp_b = 1> __device__ __forceinline__ void wgmma_n192(float* d, uint64_t descA, uint64_t descB) {
  asm volatile("{\n.reg .pred p;\nsetp.ne.b32 p, %98, 0;\n"
               "wgmma.mma_async.sync.aligned.m64n192k16.f32.bf16.bf16 {%0,%1,%2,%3,%4,%5,%6,%7,%8,%9,%10,%11,%12,%13,%14,%15,%16,%17,%18,%19,%20,%21,%22,%23,%24,%25,%26,%27,%28,%29,%30,%31,%32,%33,%34,%35,%36,%37,%38,%39,%40,%41,%42,%43,%44,%45,%46,%47,%48,%49,%50,%51,%52,%53,%54,%55,%56,%57,%58,%59,%60,%61,%62,%63,%64,%65,%66,%67,%68,%69,%70,%71,%72,%73,%74,%75,%76,%77,%78,%79,%80,%81,%82,%83,%84,%85,%86,%87,%88,%89,%90,%91,%92,%93,%94,%95}, %96, %97, p, 1, 1, 0, %99;\n}\n"
               : "+f"(d[0]), "+f"(d[1]), "+f"(d[2]), "+f"(d[3]), "+f"(d[4]), "+f"(d[5]), "+f"(d[6]), "+f"(d[7]), "+f"(d[8]), "+f"(d[9]), "+f"(d[10]), "+f"(d[11]), "+f"(d[12]), "+f"(d[13]), "+f"(d[14]), "+f"(d[15]), "+f"(d[16]), "+f"(d[17]), "+f"(d[18]), "+f"(d[19]), "+f"(d[20]), "+f"(d[21]), "+f"(d[22]), "+f"(d[23]), "+f"(d[24]), "+f"(d[25]), "+f"(d[26]), "+f"(d[27]), "+f"(d[28]), "+f"(d[29]), "+f"(d[30]), "+f"(d[31]), "+f"(d[32]), "+f"(d[33]), "+f"(d[34]), "+f"(d[35]), "+f"(d[36]), "+f"(d[37]), "+f"(d[38]), "+f"(d[39]), "+f"(d[40]), "+f"(d[41]), "+f"(d[42]), "+f"(d[43]), "+f"(d[44]), "+f"(d[45]), "+f"(d[46]), "+f"(d[47]), "+f"(d[48]), "+f"(d[49]), "+f"(d[50]), "+f"(d[51]), "+f"(d[52]), "+f"(d[53]), "+f"(d[54]), "+f"(d[55]), "+f"(d[56]), "+f"(d[57]), "+f"(d[58]), "+f"(d[59]), "+f"(d[60]), "+f"(d[61]), "+f"(d[62]), "+f"(d[63]), "+f"(d[64]), "+f"(d[65]), "+f"(d[66]), "+f"(d[67]), "+f"(d[68]), "+f"(d[69]), "+f"(d[70]), "+f"(d[71]), "+f"(d[72]), "+f"(d[73]), "+f"(d[74]), "+f"(d[75]), "+f"(d[76]), "+f"(d[77]), "+f"(d[78]), "+f"(d[79]), "+f"(d[80]), "+f"(d[81]), "+f"(d[82]), "+f"(d[83]), "+f"(d[84]), "+f"(d[85]), "+f"(d[86]), "+f"(d[87]), "+f"(d[88]), "+f"(d[89]), "+f"(d[90]), "+f"(d[91]), "+f"(d[92]), "+f"(d[93]), "+f"(d[94]), "+f"(d[95])
               : "l"(descA), "l"(descB), "n"(scale_d), "n"(tnsp_b));
}
template <int scale_d> __device__ __forceinline__ void wgmma4_n192(float* d, uint32_t da, uint32_t db) {
#define R_ "{%0,%1,%2,%3,%4,%5,%6,%7,%8,%9,%10,%11,%12,%13,%14,%15,%16,%17,%18,%19,%20,%21,%22,%23,%24,%25,%26,%27,%28,%29,%30,%31,%32,%33,%34,%35,%36,%37,%38,%39,%40,%41,%42,%43,%44,%45,%46,%47,%48,%49,%50,%51,%52,%53,%54,%55,%56,%57,%58,%59,%60,%61,%62,%63,%64,%65,%66,%67,%68,%69,%70,%71,%72,%73,%74,%75,%76,%77,%78,%79,%80,%81,%82,%83,%84,%85,%86,%87,%88,%89,%90,%91,%92,%93,%94,%95}"
  asm volatile("{\n.reg .pred p, q;\n.reg .b64 a, b;\nsetp.ne.b32 p, %98, 0;\nsetp.eq.b32 q, 0, 0;\nmov.b64 a, {%96, 0x40000040};\nmov.b64 b, {%97, 0x40000040};\n"
               "wgmma.mma_async.sync.aligned.m64n192k16.f32.bf16.bf16 " R_ ", a, b, p, 1, 1, 0, 1;\nadd.s64 a, a, 2;\nadd.s64 b, b, 128;\n"
               "wgmma.mma_async.sync.aligned.m64n192k16.f32.bf16.bf16 " R_ ", a, b, q, 1, 1, 0, 1;\nadd.s64 a, a, 2;\nadd.s64 b, b, 128;\n"
               "wgmma.mma_async.sync.aligned.m64n192k16.f32.bf16.bf16 " R_ ", a, b, q, 1, 1, 0, 1;\nadd.s64 a, a, 2;\nadd.s64 b, b, 128;\n"
               "wgmma.mma_async.sync.aligned.m64n192k16.f32.bf16.bf16 " R_ ", a, b, q, 1, 1, 0, 1;\n}\n"
               : "+f"(d[0]), "+f"(d[1]), "+f"(d[2]), "+f"(d[3]), "+f"(d[4]), "+f"(d[5]), "+f"(d[6]), "+f"(d[7]), "+f"(d[8]), "+f"(d[9]), "+f"(d[10]), "+f"(d[11]), "+f"(d[12]), "+f"(d[13]), "+f"(d[14]), "+f"(d[15]), "+f"(d[16]), "+f"(d[17]), "+f"(d[18]), "+f"(d[19]), "+f"(d[20]), "+f"(d[21]), "+f"(d[22]), "+f"(d[23]), "+f"(d[24]), "+f"(d[25]), "+f"(d[26]), "+f"(d[27]), "+f"(d[28]), "+f"(d[29]), "+f"(d[30]), "+f"(d[31]), "+f"(d[32]), "+f"(d[33]), "+f"(d[34]), "+f"(d[35]), "+f"(d[36]), "+f"(d[37]), "+f"(d[38]), "+f"(d[39]), "+f"(d[40]), "+f"(d[41]), "+f"(d[42]), "+f"(d[43]), "+f"(d[44]), "+f"(d[45]), "+f"(d[46]), "+f"(d[47]), "+f"(d[48]), "+f"(d[49]), "+f"(d[50]), "+f"(d[51]), "+f"(d[52]), "+f"(d[53]), "+f"(d[54]), "+f"(d[55]), "+f"(d[56]), "+f"(d[57]), "+f"(d[58]), "+f"(d[59]), "+f"(d[60]), "+f"(d[61]), "+f"(d[62]), "+f"(d[63]), "+f"(d[64]), "+f"(d[65]), "+f"(d[66]), "+f"(d[67]), "+f"(d[68]), "+f"(d[69]), "+f"(d[70]), "+f"(d[71]), "+f"(d[72]), "+f"(d[73]), "+f"(d[74]), "+f"(d[75]), "+f"(d[76]), "+f"(d[77]), "+f"(d[78]), "+f"(d[79]), "+f"(d[80]), "+f"(d[81]), "+f"(d[82]), "+f"(d[83]), "+f"(d[84]), "+f"(d[85]), "+f"(d[86]), "+f"(d[87]), "+f"(d[88]), "+f"(d[89]), "+f"(d[90]), "+f"(d[91]), "+f"(d[92]), "+f"(d[93]), "+f"(d[94]), "+f"(d[95])
               : "r"(da), "r"(db), "n"(scale_d));
#undef R_
}
template <int scale_d> __device__ __forceinline__ void wgmma4_n128(float* d, uint32_t da, uint32_t db) {
#define R_ "{%0,%1,%2,%3,%4,%5,%6,%7,%8,%9,%10,%11,%12,%13,%14,%15,%16,%17,%18,%19,%20,%21,%22,%23,%24,%25,%26,%27,%28,%29,%30,%31,%32,%33,%34,%35,%36,%37,%38,%39,%40,%41,%42,%43,%44,%45,%46,%47,%48,%49,%50,%51,%52,%53,%54,%55,%56,%57,%58,%59,%60,%61,%62,%63}"
  asm volatile("{\n.reg .pred p, q;\n.reg .b64 a, b;\nsetp.ne.b32 p, %66, 0;\nsetp.eq.b32 q, 0, 0;\nmov.b64 a, {%64, 0x40000040};\nmov.b64 b, {%65, 0x40000040};\n"
               "wgmma.mma_async.sync.aligned.m64n128k16.f32.bf16.bf16 " R_ ", a, b, p, 1, 1, 0, 1;\nadd.s64 a, a, 2;\nadd.s64 b, b, 128;\n"
               "wgmma.mma_async.sync.aligned.m64n128k16.f32.bf16.bf16 " R_ ", a, b, q, 1, 1, 0, 1;\nadd.s64 a, a, 2;\nadd.s64 b, b, 128;\n"
               "wgmma.mma_async.sync.aligned.m64n128k16.f32.bf16.bf16 " R_ ", a, b, q, 1, 1, 0, 1;\nadd.s64 a, a, 2;\nadd.s64 b, b, 128;\n"
               "wgmma.mma_async.sync.aligned.m64n128k16.f32.bf16.bf16 " R_ ", a, b, q, 1, 1, 0, 1;\n}\n"
               : "+f"(d[0]), "+f"(d[1]), "+f"(d[2]), "+f"(d[3]), "+f"(d[4]), "+f"(d[5]), "+f"(d[6]), "+f"(d[7]), "+f"(d[8]), "+f"(d[9]), "+f"(d[10]), "+f"(d[11]), "+f"(d[12]), "+f"(d[13]), "+f"(d[14]), "+f"(d[15]), "+f"(d[16]), "+f"(d[17]), "+f"(d[18]), "+f"(d[19]), "+f"(d[20]), "+f"(d[21]), "+f"(d[22]), "+f"(d[23]), "+f"(d[24]), "+f"(d[25]), "+f"(d[26]), "+f"(d[27]), "+f"(d[28]), "+f"(d[29]), "+f"(d[30]), "+f"(d[31]), "+f"(d[32]), "+f"(d[33]), "+f"(d[34]), "+f"(d[35]), "+f"(d[36]), "+f"(d[37]), "+f"(d[38]), "+f"(d[39]), "+f"(d[40]), "+f"(d[41]), "+f"(d[42]), "+f"(d[43]), "+f"(d[44]), "+f"(d[45]), "+f"(d[46]), "+f"(d[47]), "+f"(d[48]), "+f"(d[49]), "+f"(d[50]), "+f"(d[51]), "+f"(d[52]), "+f"(d[53]), "+f"(d[54]), "+f"(d[55]), "+f"(d[56]), "+f"(d[57]), "+f"(d[58]), "+f"(d[59]), "+f"(d[60]), "+f"(d[61]), "+f"(d[62]), "+f"(d[63])
               : "r"(da), "r"(db), "n"(scale_d));
#undef R_
}
template <int scale_d> __device__ __forceinline__ void wgmma_n32(float* d, uint64_t descA, uint64_t descB) {
  asm volatile("{\n.reg .pred p;\nsetp.ne.b32 p, %18, 0;\n"
               "wgmma.mma_async.sync.aligned.m64n32k16.f32.bf16.bf16 {%0,%1,%2,%3,%4,%5,%6,%7,%8,%9,%10,%11,%12,%13,%14,%15}, %16, %17, p, 1, 1, 0, 1;\n}\n"
               : "+f"(d[0]), "+f"(d[1]), "+f"(d[2]), "+f"(d[3]), "+f"(d[4]), "+f"(d[5]), "+f"(d[6]), "+f"(d[7]), "+f"(d[8]), "+f"(d[9]), "+f"(d[10]), "+f"(d[11]), "+f"(d[12]), "+f"(d[13]), "+f"(d[14]), "+f"(d[15])
               : "l"(descA), "l"(descB), "n"(scale_d));
}
template <int scale_d, int tnsp_a> __device__ __forceinline__ void wgmma_n40(float* d, uint64_t descA, uint64_t descB) {
  asm volatile("{\n.reg .pred p;\nsetp.ne.b32 p, %22, 0;\n"
               "wgmma.mma_async.sync.aligned.m64n40k16.f32.bf16.bf16 {%0,%1,%2,%3,%4,%5,%6,%7,%8,%9,%10,%11,%12,%13,%14,%15,%16,%17,%18,%19}, %20, %21, p, 1, 1, %23, 1;\n}\n"
               : "+f"(d[0]), "+f"(d[1]), "+f"(d[2]), "+f"(d[3]), "+f"(d[4]), "+f"(d[5]), "+f"(d[6]), "+f"(d[7]), "+f"(d[8]), "+f"(d[9]), "+f"(d[10]), "+f"(d[11]), "+f"(d[12]), "+f"(d[13]), "+f"(d[14]), "+f"(d[15]), "+f"(d[16]), "+f"(d[17]), "+f"(d[18]), "+f"(d[19])
               : "l"(descA), "l"(descB), "n"(scale_d), "n"(tnsp_a));
}
__device__ __forceinline__ uint64_t make_desc(uint32_t addr, uint32_t lbo_bytes, uint32_t sbo_bytes) {
  return (uint64_t)((addr & 0x3FFFF) >> 4) | ((uint64_t)(lbo_bytes >> 4) << 16) | ((uint64_t)(sbo_bytes >> 4) << 32) | (1ull << 62);
}

__device__ __forceinline__ void ldsm_x4(uint32_t addr, uint32_t& r0, uint32_t& r1, uint32_t& r2, uint32_t& r3) {
  asm volatile("ldmatrix.sync.aligned.m8n8.x4.shared.b16 {%0,%1,%2,%3}, [%4];" : "=r"(r0), "=r"(r1), "=r"(r2), "=r"(r3) : "r"(addr) : "memory");
}
__device__ __forceinline__ void ldsm_x4_t(uint32_t addr, uint32_t& r0, uint32_t& r1, uint32_t& r2, uint32_t& r3) {
  asm volatile("ldmatrix.sync.aligned.m8n8.x4.trans.shared.b16 {%0,%1,%2,%3}, [%4];" : "=r"(r0), "=r"(r1), "=r"(r2), "=r"(r3) : "r"(addr) : "memory");
}
__device__ __forceinline__ void stsm_x4(uint32_t addr, uint32_t r0, uint32_t r1, uint32_t r2, uint32_t r3) {
  asm volatile("stmatrix.sync.aligned.m8n8.x4.shared.b16 [%0], {%1,%2,%3,%4};" :: "r"(addr), "r"(r0), "r"(r1), "r"(r2), "r"(r3) : "memory");
}
__device__ __forceinline__ void sts128(uint32_t addr, uint32_t a, uint32_t b, uint32_t c, uint32_t d) {
  asm volatile("st.shared.v4.u32 [%0], {%1,%2,%3,%4};" :: "r"(addr), "r"(a), "r"(b), "r"(c), "r"(d) : "memory");
}
__device__ __forceinline__ float lds32f(uint32_t addr) {
  float v;
  asm volatile("ld.shared.f32 %0, [%1];" : "=f"(v) : "r"(addr) : "memory");
  return v;
}
__device__ __forceinline__ void sts32f(uint32_t addr, float a) {
  asm volatile("st.shared.f32 [%0], %1;" :: "r"(addr), "f"(a) : "memory");
}
__device__ __forceinline__ void mma_bf16(float (&c)[4], uint32_t a0, uint32_t a1, uint32_t a2, uint32_t a3, uint32_t b0, uint32_t b1) {
  asm volatile("mma.sync.aligned.m16n8k16.row.col.f32.bf16.bf16.f32 {%0,%1,%2,%3}, {%4,%5,%6,%7}, {%8,%9}, {%0,%1,%2,%3};"
               : "+f"(c[0]), "+f"(c[1]), "+f"(c[2]), "+f"(c[3]) : "r"(a0), "r"(a1), "r"(a2), "r"(a3), "r"(b0), "r"(b1));
}
__device__ __forceinline__ uint32_t pack_bf16(float lo, float hi) {
  uint32_t r;
  asm("cvt.rn.bf16x2.f32 %0, %1, %2;" : "=r"(r) : "f"(hi), "f"(lo));
  return r;
}
__device__ __forceinline__ float bf_lo(uint32_t v) { return __uint_as_float(v << 16); }
__device__ __forceinline__ float bf_hi(uint32_t v) { return __uint_as_float(v & 0xFFFF0000u); }
__device__ __forceinline__ void split3(float x, uint32_t& h, uint32_t& m, uint32_t& l) {
  h = pack_bf16(x, 0.f); x -= bf_lo(h);
  m = pack_bf16(x, 0.f); x -= bf_lo(m);
  l = pack_bf16(x, 0.f);
}
__device__ __forceinline__ float ex2(float x) { float r; asm("ex2.approx.ftz.f32 %0, %1;" : "=f"(r) : "f"(x)); return r; }
__device__ __forceinline__ float rcp_fast(float x) { float r; asm("rcp.approx.ftz.f32 %0, %1;" : "=f"(r) : "f"(x)); return r; }
__device__ __forceinline__ void red_v4(float* p, float a, float b, float c, float d) {
  asm volatile("red.global.add.v4.f32 [%0], {%1, %2, %3, %4};" :: "l"(p), "f"(a), "f"(b), "f"(c), "f"(d) : "memory");
}
__device__ __forceinline__ uint4 ld_ll(const uint4* p) {
  uint4 v;
  asm volatile("{\n.reg .b64 a, b;\nld.relaxed.gpu.global.v2.b64 {a, b}, [%4];\nmov.b64 {%0, %1}, a;\nmov.b64 {%2, %3}, b;\n}\n"
               : "=r"(v.x), "=r"(v.y), "=r"(v.z), "=r"(v.w) : "l"(p) : "memory");
  return v;
}
__device__ __forceinline__ void st_b64(uint2* p, uint32_t a, uint32_t b) {
  asm volatile("{\n.reg .b64 v;\nmov.b64 v, {%1, %2};\nst.relaxed.gpu.global.b64 [%0], v;\n}\n" :: "l"(p), "r"(a), "r"(b) : "memory");
}
__device__ __forceinline__ void st_b128(uint4* p, uint32_t a, uint32_t b, uint32_t c, uint32_t d) {
  asm volatile("{\n.reg .b128 v;\nmov.b128 v, {%1, %2, %3, %4};\nst.relaxed.gpu.global.b128 [%0], v;\n}\n" :: "l"(p), "r"(a), "r"(b), "r"(c), "r"(d) : "memory");
}
__device__ __forceinline__ uint4 ld_b128(const uint4* p) {
  uint4 v;
  asm volatile("{\n.reg .b128 v;\nld.relaxed.gpu.global.b128 v, [%4];\nmov.b128 {%0, %1, %2, %3}, v;\n}\n" : "=r"(v.x), "=r"(v.y), "=r"(v.z), "=r"(v.w) : "l"(p) : "memory");
  return v;
}

constexpr float LOG2E = 1.4426950408889634f;

struct Params {
  const __nv_bfloat16* x0;
  const __nv_bfloat16* wA_qkv;
  const __nv_bfloat16* wA_o;
  const __nv_bfloat16* wB_qkv;
  const __nv_bfloat16* wB_phi;
  const __nv_bfloat16* wB_o;
  __nv_bfloat16* out;
};

#define ACC_DEF(d, n) _Pragma("unroll") for (int i_ = 0; i_ < (n); i_++) asm volatile("" : "=f"(d[i_]))
#define ACC_FENCE(d, n) _Pragma("unroll") for (int i_ = 0; i_ < (n); i_++) asm volatile("" : "+f"(d[i_]) :: "memory")
#define PIN(a, n) _Pragma("unroll") for (int i_ = 0; i_ < (n); i_++) asm volatile("" : "+f"((a)[i_]))
#define PINU(a, n) _Pragma("unroll") for (int i_ = 0; i_ < (n); i_++) asm volatile("" : "+r"((a)[i_]))

#define STAGE64(acc, off, p0, KIND, SEND) { \
    uint32_t w_[4][4]; \
    _Pragma("unroll") for (int j_ = 0; j_ < 4; j_++) { \
      const int o_ = (off) + j_ * 8; \
      w_[j_][0] = pack_bf16(rs0 * acc[o_ + 0], rs0 * acc[o_ + 1]); \
      w_[j_][1] = pack_bf16(rs1 * acc[o_ + 2], rs1 * acc[o_ + 3]); \
      w_[j_][2] = pack_bf16(rs0 * acc[o_ + 4], rs0 * acc[o_ + 5]); \
      w_[j_][3] = pack_bf16(rs1 * acc[o_ + 6], rs1 * acc[o_ + 7]); \
    } \
    if ((SEND) && hsend) { \
      _Pragma("unroll") for (int j_ = 0; j_ < 4; j_++) { \
        w_[j_][0] = (w_[j_][0] & ~1u) | hbit; \
        st_b128(hbase + lane + ((KIND) * 4 + j_) * 32, w_[j_][0], w_[j_][1], w_[j_][2], w_[j_][3]); \
      } \
    } \
    _Pragma("unroll") for (int j_ = 0; j_ < 4; j_++) \
      stsm_x4((KIND) ? (p0) + (j_ >> 1) * 8192 + (srowoff >> 1) + ((((uint32_t)(j_ & 1) << 5) + lhi) ^ lsw2) \
                     : (p0) + srowoff + ((((uint32_t)j_ << 5) + lhi) ^ lsw), \
              w_[j_][0], w_[j_][1], w_[j_][2], w_[j_][3]); \
  }
#define RW(j) (((j) >> 1) * 4 + ((j) & 1))
__device__ __forceinline__ float rmax16(const float* p) {
  float m[4];
#pragma unroll
  for (int j = 0; j < 4; j++) m[j] = fmaxf(fmaxf(p[RW(j)], p[RW(j + 4)]), fmaxf(p[RW(j + 8)], p[RW(j + 12)]));
  const float r = fmaxf(fmaxf(m[0], m[1]), fmaxf(m[2], m[3]));
  return fmaxf(r, __shfl_xor_sync(0xffffffffu, r, 1));
}
__device__ __forceinline__ float rmin16(const float* p) {
  float m[4];
#pragma unroll
  for (int j = 0; j < 4; j++) m[j] = fminf(fminf(p[RW(j)], p[RW(j + 4)]), fminf(p[RW(j + 8)], p[RW(j + 12)]));
  const float r = fminf(fminf(m[0], m[1]), fminf(m[2], m[3]));
  return fminf(r, __shfl_xor_sync(0xffffffffu, r, 1));
}
__device__ __forceinline__ float exps16(float* o, const float* p, float c, float b) {
  float s[4];
#pragma unroll
  for (int j = 0; j < 16; j++) { o[j] = ex2(fmaf(p[RW(j)], c, b)); if (j < 4) s[j] = o[j]; else s[j & 3] += o[j]; }
  return (s[0] + s[1]) + (s[2] + s[3]);
}
__device__ __forceinline__ void store16(const float* e, float sum, uint32_t dst, uint32_t dsw, int c0) {
  const float inv = rcp_fast(sum + __shfl_xor_sync(0xffffffffu, sum, 1));
#pragma unroll
  for (int j = 0; j < 2; j++)
    sts128(dst + (((c0 + j) << 4) ^ dsw), pack_bf16(e[j * 8] * inv, e[j * 8 + 1] * inv), pack_bf16(e[j * 8 + 2] * inv, e[j * 8 + 3] * inv),
           pack_bf16(e[j * 8 + 4] * inv, e[j * 8 + 5] * inv), pack_bf16(e[j * 8 + 6] * inv, e[j * 8 + 7] * inv));
}
__device__ __forceinline__ void expp16(uint32_t* o, const float* p, float c, float b) {
#pragma unroll
  for (int j = 0; j < 8; j++) o[j] = pack_bf16(ex2(fmaf(p[4 * j], c, b)), ex2(fmaf(p[4 * j + 1], c, b)));
}
#define SCHED_FENCE() asm volatile("pmevent 0;" ::: "memory")

__global__ void __cluster_dims__(2, 1, 1) __launch_bounds__(384, 1)
mega_kernel(const __grid_constant__ CUtensorMap tm_x0, const __grid_constant__ CUtensorMap tm_xo, const __grid_constant__ CUtensorMap tm_xb,
            const __grid_constant__ CUtensorMap tm_o, const __grid_constant__ CUtensorMap tm_wf,
            const __grid_constant__ CUtensorMap tm_wqA, const __grid_constant__ CUtensorMap tm_wqB,
            const __grid_constant__ CUtensorMap tm_woA, const __grid_constant__ CUtensorMap tm_woB,
            const __grid_constant__ CUtensorMap tm_phi, const Params prm) {
  extern __shared__ __align__(1024) uint8_t smem_raw[];
  const uint32_t sbase = smem_u32(smem_raw);
  const uint32_t bar_full = sbase + OFF_BAR;
  const uint32_t bar_done = bar_full + 384;
  const uint32_t bar_stat = bar_full + 768, bar_stat2 = bar_full + 776, bar_epi = bar_full + 784, bar_phi = bar_full + 936  ;
  const uint32_t bar_xr = bar_full + 800, bar_lx = bar_full + 808, bar_kvf = bar_full + 816  , bar_stg = bar_full + 832, bar_o1s = bar_full + 840;
  const uint32_t bar_chk = bar_full + 848;

  const int warp = __shfl_sync(0xffffffffu, threadIdx.x >> 5, 0), lane = threadIdx.x & 31;
  uint32_t rank;
  asm volatile("mov.u32 %0, %%cluster_ctarank;" : "=r"(rank));
  const int cta = (int)blockIdx.x - NAUX;
  const int cl = cta >> 1;
  const int jj = cl & 7, cc = cl >> 3;
  const int mm = cc * 2 + (int)rank;

  unsigned epoch;
  asm volatile("ld.relaxed.gpu.global.u32 %0, [%1];" : "=r"(epoch) : "l"(&g_flags.epoch.v) : "memory");
  const unsigned ep1 = epoch + 1;
  int budget = 1 << 22;

  if (cta >= 0) {
    {
      const int tx = threadIdx.x;
      const __nv_bfloat16* pf = (tx < 128) ? prm.x0 + (size_t)(mm * 128 + tx) * D_MODEL + jj * 128
                                           : prm.wA_qkv + (size_t)(jj * 128 + (tx & 63)) * 3072 + ((tx - 128) >> 6) * 1024 + jj * 128 + rank * 64;
      if (tx < 320) asm volatile("prefetch.global.L2 [%0];" :: "l"(pf));
      else if (tx == 320) prefetch_tmap(&tm_x0);
      else if (tx == 352) prefetch_tmap(&tm_wqA);
    }
    if (threadIdx.x < 48) {
      if (threadIdx.x == 0) {
        mbar_init(bar_stat, 2); mbar_init(bar_stat2, 1); mbar_init(bar_epi, 8); mbar_init(bar_phi, 1); mbar_init(bar_phi + 8, 1);
        mbar_init(bar_xr, 1); mbar_init(bar_lx, 8); mbar_init(bar_kvf, 1); mbar_init(bar_kvf + 8, 1); mbar_init(bar_stg, 8); mbar_init(bar_o1s, 2);
      }
      mbar_init(bar_full + threadIdx.x * 8, ((threadIdx.x & ~3u) == 4 || threadIdx.x > 40) ? 2 : 1); mbar_init(bar_done + threadIdx.x * 8, 16);
      if (threadIdx.x < 11) mbar_init(bar_chk + threadIdx.x * 8, 1);
      asm volatile("fence.mbarrier_init.release.cluster;" ::: "memory");
    }
    __syncthreads();
    asm volatile("barrier.cluster.arrive.relaxed.aligned;" ::: "memory");
  }

  if (cta < 0) {
    const uint32_t buf = sbase + warp * SLOT, bar = sbase + OFF_BAR + warp * 16;
    const uint32_t lsw = (lane & 7) << 4, lhi = (lane >> 4) << 4, lrow = (lane & 15) * 128;
    const bool el = elect_one();
    if (el) {
      mbar_init(bar, 1); mbar_init(bar + 8, 1);
      asm volatile("fence.mbarrier_init.release.cluster;" ::: "memory");
    }
#pragma unroll 1
    for (int rd = 0; rd < (NLAYERS > 1 ? 5 : 2); rd++) {
      if (rd >= 2 && warp >= 8) break;
      const int tk = rd < 2 ? blockIdx.x * 12 + warp : blockIdx.x * 8 + warp;
      const int half = tk & 1;
      const int blk = rd < 2 ? (tk >> 1) * 2 + rd : (rd == 2 ? 32 + (tk >> 1) : (tk >> 1) * 2 + rd - 3);
      const CUtensorMap* tm = rd < 2 ? &tm_wqA : (rd == 2 ? &tm_wqB : &tm_wf);
      const int j0 = (blk & 15) >> 1;
#define AUX_LOAD(n) { const uint32_t d_ = buf + ((n) & 1) * 8192, b_ = bar + ((n) & 1) * 8; const int r_ = kslice(j0, 2 * (n) + half) * 64; \
        mbar_expect_tx(b_, 8192); tma_load_2d(d_, tm, b_, blk * 64, r_); tma_load_2d(d_ + 4096, tm, b_, blk * 64, r_ + 32); }
      if (el) {
        if (rd == 3) { wait_flag(&g_flags.wfready[j0].v, ep1 * 16); fence_proxy_async_global(); }
        AUX_LOAD(0); AUX_LOAD(1);
      }
      __syncwarp();
      float cs[8][4];
#pragma unroll
      for (int i = 0; i < 8; i++) cs[i][0] = cs[i][1] = cs[i][2] = cs[i][3] = 0.f;
#pragma unroll 1
      for (int n = 0; n < 8; n++) {
        const uint32_t tb = buf + (n & 1) * 8192 + lrow;
        mbar_wait(bar + (n & 1) * 8, (n >> 1) & 1);
#pragma unroll
        for (int i = 0; i < 16; i++) {
          uint32_t b0, b1, b2, b3;
          ldsm_x4_t(tb + (i >> 2) * 2048 + (((i & 3) * 32 + lhi) ^ lsw), b0, b1, b2, b3);
          mma_bf16(cs[2 * (i & 3)], 0x3F803F80u, 0x3F803F80u, 0x3F803F80u, 0x3F803F80u, b0, b1);
          mma_bf16(cs[2 * (i & 3) + 1], 0x3F803F80u, 0x3F803F80u, 0x3F803F80u, 0x3F803F80u, b2, b3);
        }
        __syncwarp();
        if (el && n < 6) AUX_LOAD(n + 2);
      }
      if (lane < 4) {
#pragma unroll
        for (int i = 0; i < 8; i++) st_b64(&g_colsum[rd >= 2][blk * 32 + i * 4 + lane][half], __float_as_uint(cs[i][0]), (__float_as_uint(cs[i][1]) & ~3u) | (ep1 & 3));
      }
      __syncwarp();
    }
  } else if (warp >= 8) {
    asm volatile("setmaxnreg.dec.sync.aligned.u32 40;");
    if (warp == 8) {
      const bool el = elect_one();
      cluster_wait();
      if (el) {
#pragma unroll 1
        for (int l = 0; l < NLAYERS; l++) {
          const uint32_t par = l & 1;
          const CUtensorMap* tqk = par ? &tm_wf : &tm_wqA;
          const CUtensorMap* tv = par ? &tm_wqB : &tm_wqA;
          const CUtensorMap* two = par ? &tm_woB : &tm_woA;
          if (l == 1) { wait_flag(&g_flags.wfready[jj].v, ep1 * 16); fence_proxy_async_global(); }
#pragma unroll 1
          for (int u = 0; u < 32; u++) {
            if (u >= 4) mbar_wait_sl(bar_done + (u - 4) * 8, par);
            else if (l) mbar_wait_sl(bar_done + (43 + u + (u >> 1)) * 8, par ^ 1);
            else if (u == 1) __nanosleep(STAG1);
            else if (u == 2) mbar_wait_sl(bar_full, 0);
            const uint32_t fb = bar_full + u * 8;
            const bool res = u < 4 ? (l || u >= 2) : (u < 8 || (u >= 18 && u < 22));
            mbar_expect_tx(fb, res ? QST : QST + SLOT);
            const int row = kslice(jj, u < 4 ? u & 1 : (u < 18 ? u - 2 : (u < 22 ? u - 6 : u - 20))) * 64 + (int)rank * 32;
            const int col = jj * 128 + (u < 4 ? u >> 1 : (u >= 18)) * 64;
            const uint32_t dst = sbase + (u & 3) * QST + rank * 4096;
            tma_load_2d_mc(dst, tqk, fb, col, row);
            tma_load_2d_mc(dst + 8192, tqk, fb, col + 1024, row);
            tma_load_2d_mc(dst + 16384, tv, fb, col + 2048, row);
          }
#pragma unroll 1
          for (int s = 0; s < 16; s++) {
            if (s < 5) { if (s != 2 && s != 4) mbar_wait_sl(bar_done + (28 + s) * 8, par); }
            else if (s != 14) mbar_wait_sl(bar_done + (27 + s - (s == 15)) * 8, par);
            if (s == 13) mbar_wait_sl(bar_o1s, par);
            const uint32_t fb = bar_full + (32 + s) * 8;
            mbar_expect_tx(fb, (s && s < 8) ? 2 * SLOT : SLOT);
            tma_load_2d_mc(sbase + rank * 8192 + (uint32_t)((WO_BSLOT >> (4 * s)) & 15) * SLOT, two, fb, jj * 128 + (int)rank * 64, wslice(jj, s) * 64);
          }
        }
      }
      __syncwarp();
    } else if (warp == 9) {
      const bool el = elect_one();
      if (el) {
        tma_load_2d(sbase + OFF_S, &tm_x0, bar_full, jj * 128, mm * 128);
        __nanosleep(STAG1);
        tma_load_2d(sbase + OFF_S + SLOT, &tm_x0, bar_full + 8, jj * 128 + 64, mm * 128);
      }
      mbar_wait_sl(bar_full, 0);
      const size_t poff = (size_t)(mm * 128 + (lane >> 3) * 32 + (jj & 3) * 8) * D_MODEL + ((jj + lane + 1) & 7) * 128 + (jj >> 2) * 16;
#define POLL_TILE(i, buf, bit) \
      if (!((rdy >> (i)) & 1)) { \
        const unsigned* pp = reinterpret_cast<const unsigned*>((buf) + poff); \
        unsigned v0 = ld_relaxed(pp); \
        __nanosleep(150); \
        unsigned v1 = ld_relaxed(pp); \
        _Pragma("unroll 1") for (int it = 0; it < (1 << 18); it++) { \
          uint32_t ok = __ballot_sync(0xffffffffu, ((v0 ^ (bit)) & 1) == 0); \
          rdy = ok & (ok >> 8) & (ok >> 16) & (ok >> 24); \
          if ((rdy >> (i)) & 1) break; \
          v0 = ld_relaxed(pp); \
          ok = __ballot_sync(0xffffffffu, ((v1 ^ (bit)) & 1) == 0); \
          rdy = ok & (ok >> 8) & (ok >> 16) & (ok >> 24); \
          if ((rdy >> (i)) & 1) break; \
          v1 = ld_relaxed(pp); \
        } \
      }
#pragma unroll 1
      for (int l = 0; l < NLAYERS; l++) {
        const uint32_t par = l & 1;
        const CUtensorMap* tx = l ? &tm_xb : &tm_x0;
        uint32_t rdy = l ? 0 : 0xFF;
        if (l) mbar_wait_sl(bar_done + 47 * 8, par ^ 1);
#pragma unroll 1
        for (int u = 4; u < 8; u++) {
          POLL_TILE(u - 4, g_xbuf, X_BIT(l - 1));
          if (el) {
            if (u == 4) PROFT(320 + l * 16);
            mbar_expect_tx(bar_chk + (u - 4) * 8, SLOT);
            tma_load_2d(sbase + OFF_RA + (u & 3) * SLOT, tx, bar_chk + (u - 4) * 8, kslice(jj, u - 2) * 64, mm * 128);
          }
        }
        if (el) {
#pragma unroll 1
          for (int u = 8; u < 34; u++) {
            if (u == 18) u = 22;
            mbar_wait_sl(bar_done + (u - 4) * 8, par);
            if (u == 8 && l) { wait_flag(&g_flags.xready[l][mm].v, ep1 * 8); fence_proxy_async_global(); }
            if (u == 32) mbar_expect_tx(bar_xr, 2 * SLOT);
            tma_load_2d(sbase + OFF_RA + (u & 3) * SLOT, tx, u < 32 ? bar_full + u * 8 : bar_xr, kslice(jj, u < 18 ? u - 2 : (u < 32 ? u - 20 : u - 32)) * 64, mm * 128);
            if (l == 0 && u < 16) prefetch_l2((const char*)prm.wB_qkv + (size_t)(cta * 8 + u - 8) * 6144 + 2048, 4096);
            if (l == 0 && u < 13 && NLAYERS > 1) {
              if (u == 8) { mbar_expect_tx(bar_phi, SLOT + 8192); tma_load_2d(sbase + OFF_PHI, &tm_phi, bar_phi, 0, jj * 128); }
              else tma_load_2d(sbase + 12 * SLOT + (u - 9) * 4096, &tm_wqB, bar_phi, jj * 128 + ((u - 9) >> 1) * 64, mm * 64 + ((u - 9) & 1) * 32);
            }
            if (l < 2 && u >= 22 && u < 26) prefetch_l2((const char*)(l ? prm.wB_o : prm.wA_o) + (size_t)cta * 16384 + (u - 22) * 4096, 4096);
          }
          wait_flag(&g_flags.oready[l][mm].v, ep1 * 8);
          fence_proxy_async_global();
          PROFT(321 + l * 16);
#pragma unroll 1
          for (int s = 1; s < 8; s++) {
            if (s == 1) mbar_wait_sl(bar_done + 30 * 8, par);
            else if (s == 2) mbar_wait_sl(bar_lx, par);
            else if (s == 4) mbar_wait_sl(bar_done + (31 + par) * 8, par);
            else if (s == 5) mbar_wait_sl(par ? bar_epi : bar_done + 32 * 8, par);
            else if (s > 5) mbar_wait_sl(bar_done + (27 + s) * 8, par);
            tma_load_2d(sbase + (uint32_t)((WO_ASLOT(par) >> (4 * s)) & 15) * SLOT, &tm_o, bar_full + (32 + s) * 8, wslice(jj, s) * 64, mm * 128);
          }
        }
        __syncwarp();
        rdy = 0;
        mbar_wait_sl(bar_epi, par);
#pragma unroll 1
        for (int s = 9; s < 16; s++) {
          POLL_TILE(s - 9, g_obuf + 64, O_BIT(l));
          if (s >= 11) mbar_wait_sl(bar_done + (24 + s) * 8, par);
          if (el) {
            if (s == 9) PROFT(322 + l * 16);
            mbar_expect_tx(bar_chk + (s - 5) * 8, SLOT);
            tma_load_2d(sbase + (uint32_t)((WO_ASLOT(par) >> (4 * s)) & 15) * SLOT, &tm_o, bar_chk + (s - 5) * 8, wslice(jj, s) * 64, mm * 128);
          }
        }
      }
      __syncwarp();
      cluster_wait();
    } else {
      const int hw = warp - 10;
      const bool el = elect_one();
      cluster_wait();
      if (hw == 0) {
        mbar_wait_sl(bar_full + 8, 0);
        if (lane < 7) prefetch_tmap(lane == 0 ? &tm_xb : lane == 1 ? &tm_o : lane == 2 ? &tm_wf : lane == 3 ? &tm_wqB : lane == 4 ? &tm_woA : lane == 5 ? &tm_woB : &tm_phi);
      } else {
#pragma unroll 1
        for (int b = 0; b < 2; b++) {
          float4* z = reinterpret_cast<float4*>(g_kv[b] + (jj * 4) * KVH + mm * (4 * KVH / 16)) + lane;
#pragma unroll
          for (int i = 0; i < 5; i++) z[i * 32] = make_float4(0.f, 0.f, 0.f, 0.f);
        }
      }
      uint32_t chkp = 0;
#define CHECK_TILES(c0, c1, bit, skip) \
      _Pragma("unroll 1") for (int c = (c0); c < (c1); c++) { \
        const uint32_t tile = sbase + (c < 4 ? 6 + c : (uint32_t)((WO_ASLOT(l & 1) >> (4 * c + 20)) & 15)) * SLOT; \
        _Pragma("unroll 1") for (int it = 0; it < (1 << 12); it++) { \
          mbar_wait_sl(bar_chk + c * 8, (chkp >> c) & 1); \
          chkp ^= 1u << c; \
          if (el && (c == 0 || c == 4)) PROFT(488 + l * 2 + (c >> 2)); \
          if (skip) break; \
          uint32_t a1 = 1, o1 = 0; \
          _Pragma("unroll") for (int i = 0; i < 16; i++) { \
            uint32_t w; \
            asm volatile("ld.shared.u32 %0, [%1];" : "=r"(w) : "r"(tile + i * 1024 + (lane & 7) * 132 + (lane >> 3) * 32) : "memory"); \
            a1 &= w; o1 |= w; \
          } \
          if (__all_sync(0xffffffffu, (((bit) ? a1 : ~o1) & 1) != 0)) break; \
          if (el) { \
            fence_proxy_async_smem(); \
            mbar_expect_tx(bar_chk + c * 8, SLOT); \
            tma_load_2d(tile, c < 4 ? &tm_xb : &tm_o, bar_chk + c * 8, (c < 4 ? kslice(jj, c + 2) : wslice(jj, c + 5)) * 64, mm * 128); \
            RETRY_COUNT(); \
          } \
        } \
        if (el) mbar_arrive_local(bar_full + (c < 4 ? 4 + c : 37 + c) * 8); \
      }
#pragma unroll 1
      for (int l = 0; l < NLAYERS; l++) {
        int lane; asm volatile("mov.u32 %0, %%laneid;" : "=r"(lane));
        if (hw) CHECK_TILES(0, 4, X_BIT(l - 1), l == 0);
        {
          mbar_wait_sl(bar_done + 32, l & 1);
          const uint4* sp = reinterpret_cast<const uint4*>(g_stats + (size_t)(mm * 128 + hw * 64) * 8) + lane;
#pragma unroll 1
          for (int hf = 0; hf < 2; hf++) {
            uint4 v[4];
            uint32_t bad;
            int it = 0;
            do {
              bad = 0;
#pragma unroll
              for (int i = 0; i < 4; i++) { v[i] = ld_ll(sp + (hf * 4 + i) * 32); bad |= (v[i].y ^ STAT_TAG(l)) | (v[i].w ^ STAT_TAG(l)); }
              bad &= 3;
              if (bad) __nanosleep(200);
            } while (bad && ++it < (1 << 16));
            __syncwarp();
            float mean = 0.f, m2 = 0.f;
#pragma unroll
            for (int i = 0; i < 4; i++) {
              float a = __uint_as_float(v[i].x) + __uint_as_float(v[i].z);
              a += __shfl_xor_sync(0xffffffffu, a, 1); a += __shfl_xor_sync(0xffffffffu, a, 2);
              a *= 0.125f;
              const float e0 = __uint_as_float(v[i].x) - a, e1 = __uint_as_float(v[i].z) - a;
              float q = fmaf(fmaf(e0, e0, e1 * e1), 128.f, __uint_as_float(v[i].y) + __uint_as_float(v[i].w));
              q += __shfl_xor_sync(0xffffffffu, q, 1); q += __shfl_xor_sync(0xffffffffu, q, 2);
              if ((lane & 3) == i) { mean = a; m2 = q; }
            }
            const uint32_t row = hw * 64 + hf * 32 + (lane & 3) * 8 + (lane >> 2);
            uint32_t h, m, lo;
            split3(-0.5f * mean, h, m, lo);
            sts128(sbase + OFF_LNA + row * 16, h | (h << 16), m | (h << 16), lo | (m << 16), m | (lo << 16));
            sts32f(sbase + OFF_ST + row * 4, rsqrtf(m2 * (1.f / 1024.f) + 1e-5f));
          }
          fence_proxy_async_smem();
          __syncwarp();
          if (el && hw) mbar_arrive_local(bar_stat);
          const uint4* src = reinterpret_cast<const uint4*>(g_colsum[l & 1][jj * 64 + hw * 32 + lane]);
          uint32_t bad;
          int it = 0;
          float c[6];
          do {
            bad = 0;
#pragma unroll
            for (int p = 0; p < 3; p++) {
              const uint4 v = ld_ll(src + p * 512);
              bad |= (v.y ^ ep1) | (v.w ^ ep1);
              c[2 * p] = __uint_as_float(v.x) + __uint_as_float(v.z); c[2 * p + 1] = __uint_as_float(v.y) + __uint_as_float(v.w);
            }
            bad &= 3;
            if (bad) __nanosleep(300);
          } while (bad && ++it < (1 << 16));
#pragma unroll
          for (int p = 0; p < 6; p++) {
            uint32_t h, m, lo;
            split3(c[p], h, m, lo);
            sts128(sbase + OFF_LNB + hw * 4096 + (p >> 1) * 1024 + lane * 32 + (p & 1) * 16, h | (m << 16), h | (lo << 16), h | (m << 16), lo | (m << 16));
          }
          fence_proxy_async_smem();
          __syncwarp();
          if (el) { mbar_arrive_local(hw ? bar_stat2 : bar_stat); PROFT(323 + l * 16 + hw); }
        }
        if (hw) {
          if (l & 1) {
#pragma unroll 1
            for (int h = 0; h < 2; h++) {
              asm volatile("bar.sync %0, 288;" :: "r"(BAR_KV + h) : "memory");
              __syncwarp();
              PROFT(331 + l * 16 + h);
              if (lane < 16) signal_release(&g_flags.kvready[(l & 2) + h][jj][lane].v);
              const unsigned* kf = &g_flags.kvready[(l & 2) + h][jj][mm].v;
              unsigned v0 = ld_relaxed(kf);
              __nanosleep(150);
              unsigned v1 = ld_relaxed(kf);
#pragma unroll 1
              for (int it = 0; it < (1 << 18); it++) {
                if (v0 == ep1 * 16) break;
                v0 = ld_relaxed(kf);
                if (v1 == ep1 * 16) break;
                v1 = ld_relaxed(kf);
              }
              fence_acquire();
              __syncwarp();
              if (el) { mbar_arrive_local(bar_kvf + h * 8); PROFT(333 + l * 16 + h); }
            }
          } else if (l == 0 && NLAYERS > 1) {
#pragma unroll 1
            for (int ph = 0; ph < 3; ph++) {
              asm volatile("bar.sync %0, 288;" :: "r"(BAR_WF + ph + (ph > 0)) : "memory");
              if (el) {
                if (ph == 1) mbar_expect_tx(bar_phi + 8, SLOT);
#pragma unroll 1
                for (int i = 0; i < 4; i++) {
                  const uint32_t a = sbase + (ph ? 10 : 12) * SLOT + i * 4096;
                  const int c0 = (ph ? 1024 : 0) + jj * 128 + (i >> 1) * 64, c1 = mm * 64 + (i & 1) * 32;
                  if (ph == 1) tma_load_2d(a, &tm_wqB, bar_phi + 8, c0, c1); else tma_store_2d(&tm_wf, a, c0, c1);
                }
                if (ph != 1) {
                  asm volatile("cp.async.bulk.commit_group;\ncp.async.bulk.wait_group.read 0;" ::: "memory");
                  mbar_arrive_local(bar_phi + ph * 4);
                }
                if (ph == 2) {
                  asm volatile("cp.async.bulk.wait_group 0;" ::: "memory");
                  signal_release(&g_flags.wfready[jj].v);
                  PROFT(335);
                }
              }
              __syncwarp();
            }
          }
        }
        if (hw) { CHECK_TILES(4, 11, O_BIT(l), false); }
        else {
#pragma unroll 1
          for (int e = 0; e < 4; e++) {
            asm volatile("bar.sync %0, 288;" :: "r"(BAR_O + e) : "memory");
            if (el) {
              PROFT(325 + l * 16 + e);
              tma_store_2d((e & 2) ? (l < NLAYERS - 1 ? &tm_xb : &tm_xo) : &tm_o, sbase + ((0xBA3C >> (4 * e)) & 15) * SLOT, jj * 128 + (e & 1) * 64, mm * 128);
              if (e != 2) bulk_commit_wait();
              if (e & 1) PROFT(480 + l * 2 + (e >> 1));
              if (e == 1) { mbar_arrive_remote(bar_o1s, 0); mbar_arrive_remote(bar_o1s, 1); }
              else if (e == 0) signal_release(&g_flags.oready[l][mm].v);
              else if (e == 3 && l < NLAYERS - 1) signal_release(&g_flags.xready[l + 1][mm].v);
              if (e & 1) PROFT(329 + l * 16 + (e >> 1));
            }
            __syncwarp();
          }
        }
      }
    }
    cluster_sync();
  } else {
    asm volatile("setmaxnreg.inc.sync.aligned.u32 232;");
    const int wg = warp >> 2;
    const int r0 = warp * 16;
    const uint32_t pK = sbase + OFF_S, pV = sbase + OFF_S + SLOT;
#define PMASKS(on, bit) const uint32_t pm0 = ((on) && t == (g & 3) && (g >> 2) == (g & 1)), pm1 = ((on) && t == (g & 3) && (g >> 2) != (g & 1)), pbit = (bit)
#define PBIT0(w) (((w) & ~pm0) | (pbit & pm0))
#define PBIT1(w) (((w) & ~pm1) | (pbit & pm1))
#define LANE_CONSTS() \
    int lane; asm volatile("mov.u32 %0, %%laneid;" : "=r"(lane)); \
    const int g = lane >> 2, t = lane & 3; \
    const uint32_t srowoff = (r0 + (lane & 15)) * 128, lsw = (lane & 7) << 4, lhi = (lane >> 4) << 4, lsw2 = (lane & 6) << 3; \
    (void)g; (void)t; (void)srowoff; (void)lsw; (void)lhi; (void)lsw2;
    uint32_t stgp = 0, peer;
    asm volatile("mapa.shared::cluster.u32 %0, %1, %2;" : "=r"(peer) : "r"(sbase), "r"(rank ^ 1));
    peer -= sbase;
    const uint32_t dA0 = (((sbase & 0x3FFFF) + wg * 8192) >> 4) | 0x10000u, dB0 = ((sbase & 0x3FFFF) >> 4) | 0x2000000u;
    cluster_wait();
#define STG_ARRIVE() { __syncwarp(); if (elect_one()) mbar_arrive_local(bar_stg); }
#define STG_WAIT() { mbar_wait(bar_stg, stgp); stgp ^= 1; }
#define PROFS() do {} while (0)
#define REL(addr) { if (elect_one()) { mbar_arrive_local(addr); asm volatile("mbarrier.arrive.shared::cluster.b64 _, [%0];" :: "r"((addr) + peer) : "memory"); } }
#define QSTEP(ACC, DA, SC, PRE) { \
      const uint32_t da = (DA), db = dB0 + (ub & 0x18) * (QST >> 7); \
      mbar_wait(ub, par); \
      PRE; \
      wgmma_fence(); \
      wgmma4_n192<SC>(ACC, da, db); \
      wgmma_commit(); PROFS(); }
#define QREL() { wgmma_wait<1>(); REL(ub + 376); ub += 8; }
#define RA_CUR (dA0 + (OFF_RA >> 4) + (ub & 0x18) * (SLOT >> 7))
#define PUMP1() { QSTEP(S1, RA_CUR, 1, {}); QREL(); }
#define PUMP0() { PUMP1(); SCHED_FENCE(); }
#define PUMP() if (h == 0) PUMP1()
#define WSTEP() { \
      const uint32_t s4 = (ub - bar_full - 256) >> 1; \
      const uint32_t da = dA0 + (((uint32_t)(WO_ASLOT(par) >> s4) & 15) << 10), db = dB0 + (((uint32_t)(WO_BSLOT >> s4) & 15) << 10); \
      mbar_wait(ub, par); \
      wgmma_fence(); \
      wgmma4_n128<1>(S1, da, db); \
      wgmma_commit(); PROFS(); \
      wgmma_wait<1>(); \
      if (s4 > par * 4) REL(ub + 376); \
      ub += 8; }
#define PUMPS(n) { _Pragma("unroll 1") for (int i_ = 0; i_ < (n); i_++) PUMP1(); }
#define SITE(n) { if ((BMASK >> (n)) & 1) { PUMP(); } else SCHED_FENCE(); }
#define LNSTEP(ACC, hh) { wgmma_fence(); wgmma_n192<1, 0>(ACC, make_desc(sbase + OFF_LNA + wg * 1024, 0, 128) ^ (1ull << 62), make_desc(sbase + OFF_LNB + (hh) * 4096, 0, 128) ^ (1ull << 62)); }
#define DRAIN_A(ACC, PMP) { \
      LANE_CONSTS(); \
      STAGE64(ACC, 64, pV, 1, 1); \
      PMP; \
      STAGE64(ACC, 32, pK, 0, 1); \
      STG_ARRIVE(); \
      _Pragma("unroll") for (int i_ = 0; i_ < 16; i_++) qa[i_] = pack_bf16(ACC[2 * i_], ACC[2 * i_ + 1]); \
      PINU(qa, 16); }
#define DRAIN_B(ACC) { \
      LANE_CONSTS(); \
      STAGE64(ACC, 64, pV, 1, 0); \
      _Pragma("unroll") for (int i_ = 0; i_ < 64; i_++) st[i_] = ACC[i_]; \
      PIN(st, 64); }
#define PUBLISH_O() { fence_proxy_async_smem(); asm volatile("bar.arrive %0, 288;" :: "r"(BAR_O + h) : "memory"); }
#define REST_P1(SKEW) { \
      mbar_wait(bar_stat2, par); \
      LNSTEP(S1, 1); \
      _Pragma("unroll 1") while (ub < bar_full + 256) { \
        if (ub == bar_full + 256 - 8 * (SKEW) && wg == 0) bar_sync<BAR_SKEW, 256>(); \
        QSTEP(S1, RA_CUR, 1, {}); \
        if (ub == bar_full + 248 && wg == 1) bar_arrive<BAR_SKEW, 256>(); \
        QREL(); \
      } \
      hbase += 256; \
      mbar_wait(bar_done + (31 - (SKEW)) * 8, par);        \
      wgmma_wait<0>(); \
      ACC_FENCE(S1, 96); \
      REL(bar_done + 31 * 8); \
      PROF(13); }
#define KV_LOAD(v, hh) { \
          const float4* kvg_ = reinterpret_cast<const float4*>(g_kv[l >> 1] + (jj * 4 + (hh) * 2 + wg) * KVH) + (warp & 3) * 32 + lane; \
          mbar_wait(bar_kvf + (hh) * 8, l >> 1); \
          _Pragma("unroll") for (int i = 0; i < 5; i++) { const float4 q_ = __ldcg(kvg_ + i * 128); (v)[i * 4] = q_.x; (v)[i * 4 + 1] = q_.y; (v)[i * 4 + 2] = q_.z; (v)[i * 4 + 3] = q_.w; } }
#define KV_TILE(v, pT) { \
          const uint32_t kd = (pT) + wg * 8192 + ((warp & 3) * 16 + (lane & 15)) * 128; \
          _Pragma("unroll") for (int i = 0; i < 2; i++) \
            stsm_x4(kd + ((i * 32 + lhi) ^ lsw), pack_bf16((v)[i * 8], (v)[i * 8 + 1]), pack_bf16((v)[i * 8 + 2], (v)[i * 8 + 3]), pack_bf16((v)[i * 8 + 4], (v)[i * 8 + 5]), pack_bf16((v)[i * 8 + 6], (v)[i * 8 + 7])); \
          stsm_x4(kd + ((64u + lhi) ^ lsw), pack_bf16((v)[16], 1.f), pack_bf16((v)[18], 1.f), 0u, 0u); }
#define O_MMA(o, pA, pB, pT) { \
          _Pragma("unroll") for (int hh = 0; hh < 2; hh++) { \
            const uint64_t da = make_desc((hh ? (pB) : (pA)) + wg * 8192, 16, 1024), db = make_desc((pT) + hh * 8192, 16, 1024); \
            _Pragma("unroll") for (int ks = 0; ks < 4; ks += 2) { \
              wgmma_n40<0, 0>((o) + hh * 48 + ks * 12, da + ks * 2, db + ks * 128); wgmma_n40<1, 0>((o) + hh * 48 + ks * 12, da + ks * 2 + 2, db + ks * 128 + 128); } \
          } \
          wgmma_commit(); }
#define O_OUT(o, pA, hp) { \
          bar_wg(wg);            \
          PMASKS(hp, O_BIT(l)); \
          _Pragma("unroll") for (int hh = 0; hh < 2; hh++) { \
            const float* x = (o) + hh * 48; \
            const float* y = x + 24; \
            const float rx0 = rcp_fast(x[17]), ry0 = rcp_fast(y[17]), rx1 = rcp_fast(x[19]), ry1 = rcp_fast(y[19]); \
            const float i0 = rcp_fast(fmaf(x[16], rx0, y[16] * ry0) + 1e-6f), i1 = rcp_fast(fmaf(x[18], rx1, y[18] * ry1) + 1e-6f); \
            const float ax0 = rx0 * i0, ay0 = ry0 * i0, ax1 = rx1 * i1, ay1 = ry1 * i1; \
            _Pragma("unroll") for (int dp = 0; dp < 2; dp++) \
              stsm_x4((pA) + srowoff + ((hh * 64 + dp * 32 + lhi) ^ lsw), \
                      PBIT0(pack_bf16(fmaf(x[dp * 8], ax0, y[dp * 8] * ay0), fmaf(x[dp * 8 + 1], ax0, y[dp * 8 + 1] * ay0))), \
                      PBIT0(pack_bf16(fmaf(x[dp * 8 + 2], ax1, y[dp * 8 + 2] * ay1), fmaf(x[dp * 8 + 3], ax1, y[dp * 8 + 3] * ay1))), \
                      PBIT1(pack_bf16(fmaf(x[dp * 8 + 4], ax0, y[dp * 8 + 4] * ay0), fmaf(x[dp * 8 + 5], ax0, y[dp * 8 + 5] * ay0))), \
                      PBIT1(pack_bf16(fmaf(x[dp * 8 + 6], ax1, y[dp * 8 + 6] * ay1), fmaf(x[dp * 8 + 7], ax1, y[dp * 8 + 7] * ay1)))); \
          } \
          fence_proxy_async_smem(); \
          bar_arrive<BAR_O + (hp), 288>(); }
#define FOLD(tile, rd) { \
          LANE_CONSTS(); \
          float d[32]; \
          ACC_DEF(d, 32); \
          mbar_wait(bar_phi + (rd) * 8, 0); \
          wgmma_fence(); \
          _Pragma("unroll") for (int i = 0; i < 2; i++) { \
            const uint64_t da = make_desc((tile) + wg * 8192 + i * 64, 16, 1024); \
            const uint64_t db = make_desc(sbase + OFF_PHI + wg * 4096 + i * 2048, 16, 512) ^ (3ull << 62); \
            wgmma_n32<0>(d + i * 16, da, db); wgmma_n32<1>(d + i * 16, da + 2, db + 64); \
          } \
          wgmma_commit(); \
          PUMP0(); \
          ACC_FENCE(d, 32); \
          bar_wg(wg); \
          _Pragma("unroll") for (int i = 0; i < 4; i++) { \
            const float* x = d + (i & 1) * 8 + (i >> 1) * 2; \
            sts128((tile) + wg * 8192 + ((warp & 3) * 16 + (i >> 1) * 8 + g) * 128 + (((2 * t + (i & 1)) ^ g) << 4), \
                   pack_bf16(x[0], x[1]), pack_bf16(x[4], x[5]), pack_bf16(x[16], x[17]), pack_bf16(x[20], x[21])); \
          } \
          fence_proxy_async_smem(); \
          bar_arrive<BAR_WF + 3 * (rd), 288>(); }
#define LOAD_X0(base) \
      _Pragma("unroll") for (int j = 0; j < 8; j++) { \
        uint32_t x0, x1, x2, x3; \
        ldsm_x4((base) + (j >> 2) * SLOT + srowoff + ((((uint32_t)(j & 3) << 5) + lhi) ^ lsw), x0, x1, x2, x3); \
        S1[j * 8 + 0] = bf_lo(x0); S1[j * 8 + 1] = bf_hi(x0); S1[j * 8 + 2] = bf_lo(x1); S1[j * 8 + 3] = bf_hi(x1); \
        S1[j * 8 + 4] = bf_lo(x2); S1[j * 8 + 5] = bf_hi(x2); S1[j * 8 + 6] = bf_lo(x3); S1[j * 8 + 7] = bf_hi(x3); \
      }
#define LOAD_X() { \
      wgmma_wait<0>(); \
      mbar_wait(bar_xr, par); \
      LOAD_X0(sbase + OFF_RA); \
      ACC_FENCE(S1, 64); \
      __syncwarp(); if (elect_one()) mbar_arrive_local(bar_lx); }

    float S1[96];
#pragma unroll
    for (int i = 0; i < 64; i++) S1[i] = 0.f;
#pragma unroll 1
    for (int l = 0; l < NLAYERS; l++) {
      const uint32_t par = l & 1;
      bar_wg(wg);
      PROF(0);
      uint32_t ub = bar_full;
      const bool hsend = (warp == 7) && (mm < 15);
      const uint32_t hbit = (NLAYERS > 2) ? (l == 0) : (ep1 & 1);
      float S0[96];
      {
        LANE_CONSTS();
        ACC_DEF(S0, 96);
        QSTEP(S0, dA0 + (OFF_S >> 4), 0, {});
        ub += 8;
        PROF(1);
        if (l == 0) { mbar_wait(ub, 0); LOAD_X0(pK); }
        SCHED_FENCE();
        {
          float a0 = S1[0], a1 = S1[2], b0 = S1[1], b1 = S1[3];
#pragma unroll
          for (int i = 4; i < 64; i += 4) { a0 += S1[i]; b0 += S1[i + 1]; a1 += S1[i + 2]; b1 += S1[i + 3]; }
          a0 += b0; a1 += b1;
          a0 += __shfl_xor_sync(0xffffffffu, a0, 1); a1 += __shfl_xor_sync(0xffffffffu, a1, 1);
          a0 += __shfl_xor_sync(0xffffffffu, a0, 2); a1 += __shfl_xor_sync(0xffffffffu, a1, 2);
          a0 *= (1.f / 128.f); a1 *= (1.f / 128.f);
          asm volatile("" : "+f"(a0), "+f"(a1));
          QSTEP(S0, dA0 + ((OFF_S + SLOT) >> 4), 1, wgmma_wait<0>());
          REL(ub + 376); ub += 8;
          SCHED_FENCE();
          float q0 = 0.f, q1 = 0.f;
          b0 = 0.f; b1 = 0.f;
#pragma unroll
          for (int i = 0; i < 64; i += 4) {
            const float d0 = S1[i] - a0, d1 = S1[i + 1] - a0, d2 = S1[i + 2] - a1, d3 = S1[i + 3] - a1;
            q0 = fmaf(d0, d0, q0); b0 = fmaf(d1, d1, b0); q1 = fmaf(d2, d2, q1); b1 = fmaf(d3, d3, b1);
          }
          q0 += b0; q1 += b1;
          q0 += __shfl_xor_sync(0xffffffffu, q0, 1); q1 += __shfl_xor_sync(0xffffffffu, q1, 1);
          q0 += __shfl_xor_sync(0xffffffffu, q0, 2); q1 += __shfl_xor_sync(0xffffffffu, q1, 2);
          if (t < 2) st_b64(g_stats + (size_t)(mm * 128 + r0 + g + t * 8) * 8 + jj, __float_as_uint(t ? a1 : a0), (__float_as_uint(t ? q1 : q0) & ~3u) | STAT_TAG(l));
        }
        ACC_DEF(S1, 96);
        QSTEP(S1, dA0 + (OFF_S >> 4), 0, {});
        QREL();
        QSTEP(S1, dA0 + ((OFF_S + SLOT) >> 4), 1, {});
        QREL();
#pragma unroll 1
        for (int i = 0; i < 14; i++) {
          QSTEP(S0, RA_CUR, 1, {});
          if (i == 0) PROF(2);
          QREL();
        }
      }
      LANE_CONSTS();
      uint4* hbase = g_halo + (size_t)(mm * 8 + jj) * 512;
      mbar_wait(bar_stat, par);
      LNSTEP(S0, 0);
      wgmma_commit();
      const float rs0 = lds32f(sbase + OFF_ST + (r0 + g) * 4), rs1 = lds32f(sbase + OFF_ST + (r0 + g + 8) * 4);
      PUMP0();
      ACC_FENCE(S0, 96);
      PROF(3);
      if (!par) {
        constexpr uint32_t par = 0;
        uint32_t qa[16];
        DRAIN_A(S0, PUMP0());
#pragma unroll 1
        for (int h = 0; h < 2; h++) {
          const uint32_t pO = sbase + (h ? 3 : 12) * SLOT;
          PROF(4 + h * 12);
          const bool fold = (l == 0 && h == 0 && NLAYERS > 1);
          if (fold) FOLD(pO, 0) else if (h == 0) PUMPS(HPUMP1);
          LANE_CONSTS();
          uint4 hv[8];
#pragma unroll
          for (int i = 0; i < 8; i++) hv[i] = make_uint4(hbit, 0, 0, 0);
          const bool hrec = (warp == 0 && mm > 0);
          if (hrec) {
#pragma unroll
            for (int i = 0; i < 8; i++) hv[i] = ld_b128(hbase + lane - 8 * 512 + i * 32);
          }
          if (h) LOAD_X() else PUMPS(HPUMP2);
          const uint32_t halo = sbase + OFF_HALO;
          STG_WAIT();
          if (warp == 0) {
#pragma unroll 1
            for (int it = 0; it < (1 << 16); it++) {
              uint32_t bad = 0;
#pragma unroll
              for (int i = 0; i < 8; i++) bad |= hv[i].x ^ hbit;
              if (__all_sync(0xffffffffu, (bad & 1) == 0)) break;
#pragma unroll
              for (int i = 0; i < 8; i++) hv[i] = ld_b128(hbase + lane - 8 * 512 + i * 32);
            }
#pragma unroll
            for (int i = 0; i < 8; i++)
              stsm_x4(i < 4 ? halo + srowoff + ((((uint32_t)i << 5) + lhi) ^ lsw)
                            : halo + (srowoff >> 1) + (i >> 1) * 1024 + ((((uint32_t)(i & 1) << 5) + lhi) ^ lsw2), hv[i].x, hv[i].y, hv[i].z, hv[i].w);
            __syncwarp();
          }
          PROF(5 + h * 12);
          const uint32_t kb1 = pK + r0 * 128, vb1 = pV + r0 * 64;
          const uint32_t kb0 = r0 ? kb1 - 2048 : halo, vb0 = r0 ? vb1 - 1024 : halo + 2048;
          const uint32_t vhs = r0 ? 8192 : 1024;
          float s[2][4][4];
          {
            uint32_t kf[2][4][4];
#pragma unroll
            for (int i = 0; i < 8; i++) {
              const int hh = i >> 2, jb = i & 3;
              ldsm_x4(((jb < 2) ? kb0 : kb1) + ((jb & 1) * 8 + (lane & 7)) * 128 + ((hh * 64 + ((lane >> 3) << 4)) ^ lsw), kf[hh][jb][0], kf[hh][jb][1], kf[hh][jb][2], kf[hh][jb][3]);
              s[hh][jb][0] = s[hh][jb][1] = s[hh][jb][2] = s[hh][jb][3] = 0.f;
            }
#pragma unroll
            for (int ks = 0; ks < 2; ks++)
#pragma unroll
              for (int i = 0; i < 8; i++) {
                const int hh = i >> 2, jb = i & 3;
                mma_bf16(s[hh][jb], qa[hh * 8 + ks * 4], qa[hh * 8 + ks * 4 + 1], qa[hh * 8 + ks * 4 + 2], qa[hh * 8 + ks * 4 + 3], kf[hh][jb][ks * 2], kf[hh][jb][ks * 2 + 1]);
              }
          }
          PUMP();
          if (fold) bar_arrive<BAR_WF + 2, 288>();
          PROF(6 + h * 12);
          const bool e = g & 1, hb = (2 * t + (g & 1)) <= g;
          uint32_t vf[2][2][2][4];
#pragma unroll
          for (int i = 0; i < 8; i++) {
            const int hh = i >> 2, ks = (i >> 1) & 1, dp = i & 1;
            ldsm_x4_t((ks ? vb1 + hh * 8192 : vb0 + hh * vhs) + (lane & 15) * 64 + ((dp * 32 + lhi) ^ lsw2), vf[hh][ks][dp][0], vf[hh][ks][dp][1], vf[hh][ks][dp][2], vf[hh][ks][dp][3]);
          }
          float va[2][2], vb[2][2], mx[2][2];
#pragma unroll
          for (int hh = 0; hh < 2; hh++) {
            va[hh][0] = e ? s[hh][1][1] : s[hh][1][0];
            vb[hh][0] = hb ? (e ? s[hh][2][1] : s[hh][2][0]) : (e ? s[hh][0][1] : s[hh][0][0]);
            va[hh][1] = e ? s[hh][2][3] : s[hh][2][2];
            vb[hh][1] = hb ? (e ? s[hh][3][3] : s[hh][3][2]) : (e ? s[hh][1][3] : s[hh][1][2]);
          }
          if (warp == 0 && mm == 0) {
#pragma unroll
            for (int hh = 0; hh < 2; hh++) { va[hh][0] = -INFINITY; if (!hb) { vb[hh][0] = -INFINITY; vb[hh][1] = -INFINITY; } }
          }
#pragma unroll
          for (int i = 0; i < 4; i++) mx[i >> 1][i & 1] = fmaxf(va[i >> 1][i & 1], vb[i >> 1][i & 1]);
#pragma unroll
          for (int o = 1; o <= 2; o <<= 1)
#pragma unroll
            for (int i = 0; i < 4; i++) mx[i >> 1][i & 1] = fmaxf(mx[i >> 1][i & 1], __shfl_xor_sync(0xffffffffu, mx[i >> 1][i & 1], o));
          const float sc0 = rs0 * (0.17677669529663687f * LOG2E), sc1 = rs1 * (0.17677669529663687f * LOG2E);
#pragma unroll
          for (int i = 0; i < 4; i++) {
            const float sc = (i & 1) ? sc1 : sc0, m = mx[i >> 1][i & 1];
            va[i >> 1][i & 1] = ex2((va[i >> 1][i & 1] - m) * sc); vb[i >> 1][i & 1] = ex2((vb[i >> 1][i & 1] - m) * sc);
            mx[i >> 1][i & 1] = va[i >> 1][i & 1] + vb[i >> 1][i & 1];
          }
          if (h == 0 && ASITE) { PIN(&va[0][0], 4); PIN(&vb[0][0], 4); PIN(&mx[0][0], 4); PUMP1(); }
#pragma unroll
          for (int o = 1; o <= 2; o <<= 1)
#pragma unroll
            for (int i = 0; i < 4; i++) mx[i >> 1][i & 1] += __shfl_xor_sync(0xffffffffu, mx[i >> 1][i & 1], o);
          const uint32_t selA = e ? 0x1044 : 0x4410, selB = e ? 0x3244 : 0x4432, selL = hb ? 0x4444 : selB, selH = hb ? selB : 0x4444;
          float o[2][4][4];
          uint32_t pa[2][6];
#pragma unroll
          for (int hh = 0; hh < 2; hh++) {
            const float i0 = rcp_fast(mx[hh][0]), i1 = rcp_fast(mx[hh][1]);
            const uint32_t w0 = pack_bf16(va[hh][0] * i0, vb[hh][0] * i0), w1 = pack_bf16(va[hh][1] * i1, vb[hh][1] * i1);
            pa[hh][0] = __byte_perm(w0, 0, selL); pa[hh][1] = __byte_perm(w0, 0, selA); pa[hh][2] = __byte_perm(w1, 0, selL);
            pa[hh][3] = __byte_perm(w0, 0, selH); pa[hh][4] = __byte_perm(w1, 0, selA); pa[hh][5] = __byte_perm(w1, 0, selH);
#pragma unroll
            for (int dj = 0; dj < 4; dj++) { o[hh][dj][0] = o[hh][dj][1] = o[hh][dj][2] = o[hh][dj][3] = 0.f; }
          }
          PROF(7 + h * 12);
#pragma unroll
          for (int i = 0; i < 8; i++) mma_bf16(o[i >> 2][i & 3], pa[i >> 2][0], 0u, pa[i >> 2][1], pa[i >> 2][2], vf[i >> 2][0][(i >> 1) & 1][(i & 1) * 2], vf[i >> 2][0][(i >> 1) & 1][(i & 1) * 2 + 1]);
#pragma unroll
          for (int i = 0; i < 8; i++) mma_bf16(o[i >> 2][i & 3], pa[i >> 2][3], pa[i >> 2][4], 0u, pa[i >> 2][5], vf[i >> 2][1][(i >> 1) & 1][(i & 1) * 2], vf[i >> 2][1][(i >> 1) & 1][(i & 1) * 2 + 1]);
          if (h == 0) PUMP1() else mbar_wait(bar_done + 30 * 8, par);
          if (fold) mbar_wait(bar_phi, 1);
#pragma unroll
          for (int i = 0; i < 4; i++) {
            const int hh = i >> 1, dp = i & 1;
            PMASKS(h, O_BIT(l));
            stsm_x4(pO + srowoff + ((hh * 64 + dp * 32 + lhi) ^ lsw), PBIT0(pack_bf16(o[hh][dp * 2][0], o[hh][dp * 2][1])), PBIT0(pack_bf16(o[hh][dp * 2][2], o[hh][dp * 2][3])),
                    PBIT1(pack_bf16(o[hh][dp * 2 + 1][0], o[hh][dp * 2 + 1][1])), PBIT1(pack_bf16(o[hh][dp * 2 + 1][2], o[hh][dp * 2 + 1][3])));
          }
          PUBLISH_O();
          PROF(11 + h * 12);
          if (h) break;
          if (fold) { PUMPS(FPUMP); FOLD(pK, 1); }
          REST_P1(ASKEW);
          if (fold) mbar_wait(bar_phi + 8, 1);
          DRAIN_A(S1, {});
        }
      } else {
        constexpr uint32_t par = 1;
        float st[64];
        DRAIN_B(S0);
        if (warp < 2) sts128(sbase + OFF_ONES + warp * 512 + lane * 16, 0x3F803F80u, 0x3F803F80u, 0x3F803F80u, 0x3F803F80u);
        const float c0 = rs0 * LOG2E, c1 = rs1 * LOG2E;
#pragma unroll 1
        for (int h = 0; h < 2; h++) {
          const uint32_t pO = sbase + (h ? 3 : 12) * SLOT, pP = sbase + (h ? 9 : 10) * SLOT;
          PROF(4 + h * 12);
          SITE(0);
          LANE_CONSTS();
          const uint32_t dsw = (uint32_t)(g ^ (2 * t)) << 4;
          const float* pk = st + 32;
          float4* kvg = reinterpret_cast<float4*>(g_kv[l >> 1] + (jj * 4 + h * 2 + wg) * KVH) + (warp & 3) * 32 + lane;
          const uint32_t dst = ((t & 2) ? pP : pO) + (r0 + g) * 128;
          float mq[4];
          {
            float e[16], f[16];
            float mn0 = rmin16(pk);
            asm volatile("" : "+f"(mn0)); SCHED_FENCE();
            float sa = exps16(e, pk, -c0, mn0 * c0), mx0 = rmax16(pk);
            asm volatile("" : "+f"(sa), "+f"(mx0)); PIN(e, 16); SITE(1);
            store16(e, sa, dst, dsw, 4);
            float sb = exps16(f, pk, c0, -mx0 * c0), mn1 = rmin16(pk + 2);
            asm volatile("" : "+f"(sb), "+f"(mn1)); PIN(f, 16); SITE(2);
            float kv0[20];
#pragma unroll
            for (int i = 0; i < 20; i++) kv0[i] = 0.f;
            if (h) KV_LOAD(kv0, 0);
            store16(f, sb, dst, dsw, 0);
            float sc = exps16(e, pk + 2, -c1, mn1 * c1), mx1 = rmax16(pk + 2);
            asm volatile("" : "+f"(sc), "+f"(mx1)); PIN(e, 16); SITE(3);
            store16(e, sc, dst + 1024, dsw, 4);
            float sd = exps16(f, pk + 2, c1, -mx1 * c1);
            asm volatile("" : "+f"(sd)); PIN(f, 16); SITE(4);
            store16(f, sd, dst + 1024, dsw, 0);
            if (h) KV_TILE(kv0, sbase + 8 * SLOT);
          }
          fence_proxy_async_smem();
          STG_ARRIVE();
          PROF(5 + h * 12);
          uint32_t fq[32];
          {
            const uint64_t dp = make_desc(wg ? pP : pO, 16, 1024);
            const uint64_t dv = (make_desc(pV + wg * 8192, OFF_ONES - OFF_S - SLOT - wg * 8192, 512) ^ (3ull << 62));
            constexpr uint64_t DVS = 64ull - (64ull << 16);
            mq[0] = rmin16(st);
            asm volatile("" : "+f"(mq[0])); SITE(5);
            STG_WAIT();
            PROF(8 + h * 12);
#define KV_MMA() \
              float kv[20]; \
              ACC_DEF(kv, 20); \
              wgmma_fence(); \
              _Pragma("unroll") for (int ks = 0; ks < 8; ks++) { if (ks == 0) wgmma_n40<0, 1>(kv, dp, dv); else wgmma_n40<1, 1>(kv, dp + ks * 128, dv + ks * DVS); } \
              wgmma_commit();
#define KV_OUT(...) { \
              SCHED_FENCE(); \
              mq[1] = rmax16(st); mq[2] = rmin16(st + 2); mq[3] = rmax16(st + 2); \
              asm volatile("" : "+f"(mq[1]), "+f"(mq[2]), "+f"(mq[3])); \
              PROF(9 + h * 12); \
              __VA_ARGS__; \
              PROF(10 + h * 12); \
              ACC_FENCE(kv, 20); \
              _Pragma("unroll") for (int i = 0; i < 5; i++) red_v4(reinterpret_cast<float*>(kvg + i * 128), kv[i * 4], kv[i * 4 + 1], kv[i * 4 + 2], kv[i * 4 + 3]); \
              asm volatile("bar.arrive %0, 288;" :: "r"(BAR_KV + h) : "memory"); \
              STG_ARRIVE(); \
              PROF(6 + h * 12); }
            if (h == 0) { KV_MMA(); KV_OUT(PUMP0()); } else {
              float o[96];
              wgmma_wait<0>();
              ACC_DEF(o, 96);
              KV_MMA();
              KV_OUT({ wgmma_fence(); O_MMA(o, sbase + 12 * SLOT, sbase + 10 * SLOT, sbase + 8 * SLOT); wgmma_wait<1>(); });
              wgmma_wait<0>();
              ACC_FENCE(o, 20); ACC_FENCE((o + 24), 20); ACC_FENCE((o + 48), 20); ACC_FENCE((o + 72), 20);
              O_OUT(o, sbase + 12 * SLOT, 0);
              PROF(26);
              LOAD_X();
            }
          }
          expp16(fq, st, -c0, mq[0] * c0);
          PINU(fq, 8); SITE(6);
          expp16(fq + 8, st, c0, -mq[1] * c0);
          PINU(fq + 8, 8); SITE(7);
          STG_WAIT();
#pragma unroll
          for (int i = 0; i < 4; i++) sts128(dst + (((((i & 2) ? 0 : 4) + (i & 1)) << 4) ^ dsw), fq[i * 4], fq[i * 4 + 1], fq[i * 4 + 2], fq[i * 4 + 3]);
          expp16(fq + 16, st + 2, -c1, mq[2] * c1);
          PINU(fq + 16, 8); SITE(8);
          expp16(fq + 24, st + 2, c1, -mq[3] * c1);
#pragma unroll
          for (int i = 4; i < 8; i++) sts128(dst + 1024 + (((((i & 2) ? 0 : 4) + (i & 1)) << 4) ^ dsw), fq[i * 4], fq[i * 4 + 1], fq[i * 4 + 2], fq[i * 4 + 3]);
          PROF(7 + h * 12);
          if (h) break;
          REST_P1(1);
          DRAIN_B(S1);
        }
        {
          LANE_CONSTS();
          bar_wg(wg);
          WSTEP();
          wgmma_wait<0>();
          REL(bar_done + 32 * 8);
          float o[96];
          KV_LOAD(o, 1);
          PROF(32);
          KV_TILE(o, pV);
          fence_proxy_async_smem();
          STG_ARRIVE();
          ACC_DEF(o, 96);
          STG_WAIT();
          PROF(33);
          wgmma_fence();
          O_MMA(o, sbase + 3 * SLOT, sbase + 9 * SLOT, pV);
          wgmma_wait<0>();
          ACC_FENCE(o, 20); ACC_FENCE((o + 24), 20); ACC_FENCE((o + 48), 20); ACC_FENCE((o + 72), 20);
          O_OUT(o, sbase + 3 * SLOT, 1);
          PROF(34);
        }
      }
      __syncwarp();
      if (elect_one()) mbar_arrive_local(bar_epi);
      bar_wg(wg);
#pragma unroll 1
      while (ub < bar_full + 384) {
        WSTEP();
        if (ub == bar_full + 8 * 41) PROF(35);
        if (ub == bar_full + 8 * 42) PROF(36);
      }
      wgmma_wait<0>();
      ACC_FENCE(S1, 64);
      REL(bar_done + 47 * 8);
      PROF(37);
      {
      LANE_CONSTS();
#pragma unroll
      for (int j = 0; j < 8; j++) {
        PMASKS(l < NLAYERS - 1 && j < 4, X_BIT(l));
        stsm_x4(pK + (j >> 2) * SLOT + srowoff + ((((uint32_t)(j & 3) << 5) + lhi) ^ lsw),
                PBIT0(pack_bf16(S1[j * 8 + 0], S1[j * 8 + 1])), PBIT0(pack_bf16(S1[j * 8 + 2], S1[j * 8 + 3])),
                PBIT1(pack_bf16(S1[j * 8 + 4], S1[j * 8 + 5])), PBIT1(pack_bf16(S1[j * 8 + 6], S1[j * 8 + 7])));
        if (j == 3) { fence_proxy_async_smem(); bar_arrive<BAR_O + 2, 288>(); }
      }
      }
      fence_proxy_async_smem();
      bar_arrive<BAR_O + 3, 288>();
      PROF(38);
    }
    const int tid = threadIdx.x;
    if (tid == 0) {
      unsigned old = atomicAdd(&g_flags.done.v, 1);
      if (old == ep1 * NMAIN - 1) {
        asm volatile("st.relaxed.gpu.global.u32 [%0], %1;" :: "l"(&g_flags.epoch.v), "r"(ep1) : "memory");
      }
    }
    __syncwarp();
    cluster_sync();
  }
}

typedef CUresult (*PFN_encode)(CUtensorMap*, CUtensorMapDataType, cuuint32_t, void*, const cuuint64_t*, const cuuint64_t*,
                               const cuuint32_t*, const cuuint32_t*, CUtensorMapInterleave, CUtensorMapSwizzle,
                               CUtensorMapL2promotion, CUtensorMapFloatOOBfill);

CUtensorMap make_map(PFN_encode enc, const void* ptr, uint64_t inner, uint64_t outer, uint32_t box_inner, uint32_t box_outer,
                     CUtensorMapSwizzle swz = CU_TENSOR_MAP_SWIZZLE_128B) {
  CUtensorMap m;
  cuuint64_t dims[2] = {inner, outer};
  cuuint64_t strides[1] = {inner * 2};
  cuuint32_t box[2] = {box_inner, box_outer};
  cuuint32_t es[2] = {1, 1};
  enc(&m, CU_TENSOR_MAP_DATA_TYPE_BFLOAT16, 2, const_cast<void*>(ptr), dims, strides, box, es, CU_TENSOR_MAP_INTERLEAVE_NONE,
      swz, CU_TENSOR_MAP_L2_PROMOTION_L2_256B, CU_TENSOR_MAP_FLOAT_OOB_FILL_NONE);
  return m;
}

}

extern "C" void kernel_launch(void* const* d_in, const int* in_sizes, int n_in, void* d_out, int out_size) {
  (void)in_sizes; (void)n_in; (void)out_size;
  static PFN_encode enc = nullptr;
  if (!enc) {
    void* fn = nullptr;
    cudaDriverEntryPointQueryResult qr;
    cudaGetDriverEntryPoint("cuTensorMapEncodeTiled", &fn, cudaEnableDefault, &qr);
    enc = (PFN_encode)fn;
    cudaFuncSetAttribute(mega_kernel, cudaFuncAttributeMaxDynamicSharedMemorySize, SMEM_BYTES);
  }
  Params prm;
  prm.x0 = (const __nv_bfloat16*)d_in[0];
  prm.wA_qkv = (const __nv_bfloat16*)d_in[1];
  prm.wA_o = (const __nv_bfloat16*)d_in[2];
  prm.wB_qkv = (const __nv_bfloat16*)d_in[4];
  prm.wB_phi = (const __nv_bfloat16*)d_in[5];
  prm.wB_o = (const __nv_bfloat16*)d_in[6];
  prm.out = (__nv_bfloat16*)d_out;
  void *obuf = nullptr, *xbuf = nullptr, *wf = nullptr;
  cudaGetSymbolAddress(&obuf, g_obuf);
  cudaGetSymbolAddress(&xbuf, g_xbuf);
  cudaGetSymbolAddress(&wf, g_wfold);
  CUtensorMap tm_x0 = make_map(enc, d_in[0], D_MODEL, S_LEN, 64, 128);
  CUtensorMap tm_xo = make_map(enc, d_out, D_MODEL, S_LEN, 64, 128);
  CUtensorMap tm_xb = make_map(enc, xbuf, D_MODEL, S_LEN, 64, 128);
  CUtensorMap tm_o = make_map(enc, obuf, D_MODEL, S_LEN, 64, 128);
  CUtensorMap tm_wf = make_map(enc, wf, 2048, D_MODEL, 64, 32);
  CUtensorMap tm_wqA = make_map(enc, d_in[1], 3 * D_MODEL, D_MODEL, 64, 32);
  CUtensorMap tm_wqB = make_map(enc, prm.wB_qkv, 3 * D_MODEL, D_MODEL, 64, 32);
  CUtensorMap tm_woA = make_map(enc, prm.wA_o, D_MODEL, D_MODEL, 64, 64);
  CUtensorMap tm_woB = make_map(enc, prm.wB_o, D_MODEL, D_MODEL, 64, 64);
  CUtensorMap tm_phi = make_map(enc, prm.wB_phi, 32, 1024, 32, 128, CU_TENSOR_MAP_SWIZZLE_64B);
  mega_kernel<<<NMAIN + NAUX, 384, SMEM_BYTES>>>(tm_x0, tm_xo, tm_xb, tm_o, tm_wf, tm_wqA, tm_wqB, tm_woA, tm_woB, tm_phi, prm);
}
```

```cpp
#include <cuda_runtime.h>
#include <cuda.h>
#include <cuda_bf16.h>
#include <stdint.h>

#define NLAYERS 4

#define STAG1 300
#define HPUMP1 2
#define HPUMP2 2
#define ASKEW 2
#define FPUMP 2
#define PFGAP 100
#define BMASK 0x1FF
#define ASITE 1
namespace {

constexpr int S_LEN = 2048, D_MODEL = 1024;
constexpr int NAUX = 4, NMAIN = 128;
constexpr int SLOT = 16384;
constexpr int QST = 24576;
constexpr int OFF_RA = 6 * SLOT, OFF_S = 10 * SLOT;
constexpr int OFF_HALO = 13 * SLOT, OFF_LNB = OFF_HALO  , OFF_ONES = OFF_HALO + 3072;
constexpr int OFF_ST = OFF_HALO + 7168  , OFF_PHI = OFF_HALO + 8192;
constexpr int OFF_BAR = 14 * SLOT;
constexpr int OFF_LNA = OFF_BAR + 1024;
constexpr int SMEM_BYTES = OFF_LNA + 2048;
#define WO_ASLOT(par) ((par) ? 0x689C7BA3689C768Cull : 0x68C97BA368C9768Cull)
constexpr unsigned long long WO_BSLOT = 0x5432105421054210ull;
__device__ __forceinline__ int kslice(int j, int i) { return i < 2 ? 2 * j + i : (i < 9 ? 2 * ((j + i - 1) & 7) : 2 * ((j + i) & 7) + 1); }
__device__ __forceinline__ int wslice(int j, int s) { return 2 * ((j + s) & 7) + (s >> 3); }
constexpr int KVH = 5 * 128 * 4;

struct __align__(128) Flag { unsigned v; unsigned pad[31]; };
struct Flags {
  Flag xready[4][16];
  Flag oready[4][16];
  Flag kvready[4][8][16];
  Flag wfready[8];
  Flag done;
  Flag epoch;
};

__device__ Flags g_flags;
__device__ __nv_bfloat16 g_obuf[S_LEN * D_MODEL];
__device__ __nv_bfloat16 g_xbuf[S_LEN * D_MODEL];
#define O_BIT(l) ((epoch * NLAYERS + (l) + 1) & 1u)
#define X_BIT(l) ((epoch * (NLAYERS - 1) + (l) + 1) & 1u)
__device__ __nv_bfloat16 g_wfold[D_MODEL * 2048];
__device__ uint4 g_halo[16 * 8 * 512];
__device__ float g_kv[2][32 * KVH];
__device__ __align__(128) uint2 g_colsum[2][1536][2];
__device__ __align__(128) uint2 g_stats[S_LEN * 8];
#define STAT_TAG(l) ((ep1 * NLAYERS + (l) + 1) & 3u)

#define RETRY_COUNT()
#define PROFL 1
#define PROFW 0
#define KVFLAG 1
#define PROFT(i) do {} while (0)
#define PROF(i) do {} while (0)

__device__ __forceinline__ uint32_t smem_u32(const void* p) { return (uint32_t)__cvta_generic_to_shared(p); }
__device__ __forceinline__ bool elect_one() {
  uint32_t p;
  asm volatile("{\n.reg .pred p;\nelect.sync _|p, 0xffffffff;\nselp.u32 %0, 1, 0, p;\n}\n" : "=r"(p));
  return p != 0;
}
__device__ __forceinline__ void mbar_init(uint32_t bar, uint32_t cnt) {
  asm volatile("mbarrier.init.shared::cta.b64 [%0], %1;" :: "r"(bar), "r"(cnt));
}
__device__ __forceinline__ void mbar_expect_tx(uint32_t bar, uint32_t bytes) {
  asm volatile("mbarrier.arrive.expect_tx.shared::cta.b64 _, [%0], %1;" :: "r"(bar), "r"(bytes) : "memory");
}
#define mbar_wait(bar, parity) \
  asm volatile("{\n.reg .pred p, q;\nW_%=:\nmbarrier.try_wait.parity.shared::cta.b64 p, [%1], %2;\nadd.s32 %0, %0, -1;\n" \
               "setp.gt.and.s32 q, %0, 0, !p;\n@q bra W_%=;\n}\n" : "+r"(budget) : "r"((uint32_t)(bar)), "r"((uint32_t)(parity)) : "memory")
#define mbar_wait_sl(bar, parity) \
  asm volatile("{\n.reg .pred p, q;\nW_%=:\nmbarrier.try_wait.parity.shared::cta.b64 p, [%1], %2, 20000;\nadd.s32 %0, %0, -64;\n" \
               "setp.gt.and.s32 q, %0, 0, !p;\n@q bra W_%=;\n}\n" : "+r"(budget) : "r"((uint32_t)(bar)), "r"((uint32_t)(parity)) : "memory")
__device__ __forceinline__ void mbar_arrive_local(uint32_t bar) {
  asm volatile("mbarrier.arrive.shared::cta.b64 _, [%0];" :: "r"(bar) : "memory");
}
__device__ __forceinline__ void mbar_arrive_remote(uint32_t bar, uint32_t cta_rank) {
  asm volatile("{\n.reg .b32 ra;\nmapa.shared::cluster.u32 ra, %0, %1;\nmbarrier.arrive.shared::cluster.b64 _, [ra];\n}\n"
               :: "r"(bar), "r"(cta_rank) : "memory");
}
__device__ __forceinline__ void tma_load_2d(uint32_t dst, const CUtensorMap* tm, uint32_t bar, int c0, int c1) {
  asm volatile("cp.async.bulk.tensor.2d.shared::cluster.global.mbarrier::complete_tx::bytes [%0], [%1, {%3, %4}], [%2];"
               :: "r"(dst), "l"(tm), "r"(bar), "r"(c0), "r"(c1) : "memory");
}
__device__ __forceinline__ void tma_load_2d_mc(uint32_t dst, const CUtensorMap* tm, uint32_t bar, int c0, int c1) {
  asm volatile("cp.async.bulk.tensor.2d.shared::cluster.global.mbarrier::complete_tx::bytes.multicast::cluster [%0], [%1, {%3, %4}], [%2], %5;"
               :: "r"(dst), "l"(tm), "r"(bar), "r"(c0), "r"(c1), "h"((uint16_t)3) : "memory");
}
__device__ __forceinline__ void tma_store_2d(const CUtensorMap* tm, uint32_t src, int c0, int c1) {
  asm volatile("cp.async.bulk.tensor.2d.global.shared::cta.bulk_group [%0, {%2, %3}], [%1];"
               :: "l"(tm), "r"(src), "r"(c0), "r"(c1) : "memory");
}
__device__ __forceinline__ void bulk_commit_wait() {
  asm volatile("cp.async.bulk.commit_group;\ncp.async.bulk.wait_group 0;" ::: "memory");
}
__device__ __forceinline__ void prefetch_tmap(const CUtensorMap* tm) {
  asm volatile("prefetch.tensormap [%0];" :: "l"(tm) : "memory");
}
__device__ __forceinline__ void fence_proxy_async_global() { asm volatile("fence.proxy.async.global;" ::: "memory"); }
__device__ __forceinline__ void fence_proxy_async_smem() { asm volatile("fence.proxy.async.shared::cta;" ::: "memory"); }
__device__ __forceinline__ unsigned ld_relaxed(const unsigned* p) {
  unsigned v;
  asm volatile("ld.relaxed.gpu.global.u32 %0, [%1];" : "=r"(v) : "l"(p) : "memory");
  return v;
}
__device__ __forceinline__ void fence_acquire() { asm volatile("fence.acquire.gpu;" ::: "memory"); }
__device__ __forceinline__ void wait_flag(const unsigned* p, unsigned target) {
  int it = 0;
  while ((int)(ld_relaxed(p) - target) < 0 && ++it < (1 << 20)) {}
  fence_acquire();
}
__device__ __forceinline__ void signal_release(unsigned* p) {
  asm volatile("red.release.gpu.global.add.u32 [%0], 1;" :: "l"(p) : "memory");
}
template <int ID, int N> __device__ __forceinline__ void bar_arrive() { asm volatile("bar.arrive %0, %1;" :: "n"(ID), "n"(N) : "memory"); }
template <int ID, int N> __device__ __forceinline__ void bar_sync() { asm volatile("bar.sync %0, %1;" :: "n"(ID), "n"(N) : "memory"); }
__device__ __forceinline__ void bar_wg(int wg) { asm volatile("bar.sync %0, 128;" :: "r"(2 + wg) : "memory"); }
__device__ __forceinline__ void cluster_sync() {
  asm volatile("barrier.cluster.arrive.relaxed.aligned;\nbarrier.cluster.wait.aligned;" ::: "memory");
}
__device__ __forceinline__ void cluster_wait() { asm volatile("barrier.cluster.wait.acquire.aligned;" ::: "memory"); }
enum { BAR_KV = 4  , BAR_O = 7  , BAR_WF = 12  , BAR_SKEW = 13 };

__device__ __forceinline__ void wgmma_fence() { asm volatile("wgmma.fence.sync.aligned;" ::: "memory"); }
__device__ __forceinline__ void wgmma_commit() { asm volatile("wgmma.commit_group.sync.aligned;" ::: "memory"); }
template <int N> __device__ __forceinline__ void wgmma_wait() { asm volatile("wgmma.wait_group.sync.aligned %0;" :: "n"(N) : "memory"); }

template <int scale_d, int tnsp_b = 1> __device__ __forceinline__ void wgmma_n192(float* d, uint64_t descA, uint64_t descB) {
  asm volatile("{\n.reg .pred p;\nsetp.ne.b32 p, %98, 0;\n"
               "wgmma.mma_async.sync.aligned.m64n192k16.f32.bf16.bf16 {%0,%1,%2,%3,%4,%5,%6,%7,%8,%9,%10,%11,%12,%13,%14,%15,%16,%17,%18,%19,%20,%21,%22,%23,%24,%25,%26,%27,%28,%29,%30,%31,%32,%33,%34,%35,%36,%37,%38,%39,%40,%41,%42,%43,%44,%45,%46,%47,%48,%49,%50,%51,%52,%53,%54,%55,%56,%57,%58,%59,%60,%61,%62,%63,%64,%65,%66,%67,%68,%69,%70,%71,%72,%73,%74,%75,%76,%77,%78,%79,%80,%81,%82,%83,%84,%85,%86,%87,%88,%89,%90,%91,%92,%93,%94,%95}, %96, %97, p, 1, 1, 0, %99;\n}\n"
               : "+f"(d[0]), "+f"(d[1]), "+f"(d[2]), "+f"(d[3]), "+f"(d[4]), "+f"(d[5]), "+f"(d[6]), "+f"(d[7]), "+f"(d[8]), "+f"(d[9]), "+f"(d[10]), "+f"(d[11]), "+f"(d[12]), "+f"(d[13]), "+f"(d[14]), "+f"(d[15]), "+f"(d[16]), "+f"(d[17]), "+f"(d[18]), "+f"(d[19]), "+f"(d[20]), "+f"(d[21]), "+f"(d[22]), "+f"(d[23]), "+f"(d[24]), "+f"(d[25]), "+f"(d[26]), "+f"(d[27]), "+f"(d[28]), "+f"(d[29]), "+f"(d[30]), "+f"(d[31]), "+f"(d[32]), "+f"(d[33]), "+f"(d[34]), "+f"(d[35]), "+f"(d[36]), "+f"(d[37]), "+f"(d[38]), "+f"(d[39]), "+f"(d[40]), "+f"(d[41]), "+f"(d[42]), "+f"(d[43]), "+f"(d[44]), "+f"(d[45]), "+f"(d[46]), "+f"(d[47]), "+f"(d[48]), "+f"(d[49]), "+f"(d[50]), "+f"(d[51]), "+f"(d[52]), "+f"(d[53]), "+f"(d[54]), "+f"(d[55]), "+f"(d[56]), "+f"(d[57]), "+f"(d[58]), "+f"(d[59]), "+f"(d[60]), "+f"(d[61]), "+f"(d[62]), "+f"(d[63]), "+f"(d[64]), "+f"(d[65]), "+f"(d[66]), "+f"(d[67]), "+f"(d[68]), "+f"(d[69]), "+f"(d[70]), "+f"(d[71]), "+f"(d[72]), "+f"(d[73]), "+f"(d[74]), "+f"(d[75]), "+f"(d[76]), "+f"(d[77]), "+f"(d[78]), "+f"(d[79]), "+f"(d[80]), "+f"(d[81]), "+f"(d[82]), "+f"(d[83]), "+f"(d[84]), "+f"(d[85]), "+f"(d[86]), "+f"(d[87]), "+f"(d[88]), "+f"(d[89]), "+f"(d[90]), "+f"(d[91]), "+f"(d[92]), "+f"(d[93]), "+f"(d[94]), "+f"(d[95])
               : "l"(descA), "l"(descB), "n"(scale_d), "n"(tnsp_b));
}
template <int scale_d> __device__ __forceinline__ void wgmma4_n192(float* d, uint32_t da, uint32_t db) {
#define R_ "{%0,%1,%2,%3,%4,%5,%6,%7,%8,%9,%10,%11,%12,%13,%14,%15,%16,%17,%18,%19,%20,%21,%22,%23,%24,%25,%26,%27,%28,%29,%30,%31,%32,%33,%34,%35,%36,%37,%38,%39,%40,%41,%42,%43,%44,%45,%46,%47,%48,%49,%50,%51,%52,%53,%54,%55,%56,%57,%58,%59,%60,%61,%62,%63,%64,%65,%66,%67,%68,%69,%70,%71,%72,%73,%74,%75,%76,%77,%78,%79,%80,%81,%82,%83,%84,%85,%86,%87,%88,%89,%90,%91,%92,%93,%94,%95}"
  asm volatile("{\n.reg .pred p, q;\n.reg .b64 a, b;\nsetp.ne.b32 p, %98, 0;\nsetp.eq.b32 q, 0, 0;\nmov.b64 a, {%96, 0x40000040};\nmov.b64 b, {%97, 0x40000040};\n"
               "wgmma.mma_async.sync.aligned.m64n192k16.f32.bf16.bf16 " R_ ", a, b, p, 1, 1, 0, 1;\nadd.s64 a, a, 2;\nadd.s64 b, b, 128;\n"
               "wgmma.mma_async.sync.aligned.m64n192k16.f32.bf16.bf16 " R_ ", a, b, q, 1, 1, 0, 1;\nadd.s64 a, a, 2;\nadd.s64 b, b, 128;\n"
               "wgmma.mma_async.sync.aligned.m64n192k16.f32.bf16.bf16 " R_ ", a, b, q, 1, 1, 0, 1;\nadd.s64 a, a, 2;\nadd.s64 b, b, 128;\n"
               "wgmma.mma_async.sync.aligned.m64n192k16.f32.bf16.bf16 " R_ ", a, b, q, 1, 1, 0, 1;\n}\n"
               : "+f"(d[0]), "+f"(d[1]), "+f"(d[2]), "+f"(d[3]), "+f"(d[4]), "+f"(d[5]), "+f"(d[6]), "+f"(d[7]), "+f"(d[8]), "+f"(d[9]), "+f"(d[10]), "+f"(d[11]), "+f"(d[12]), "+f"(d[13]), "+f"(d[14]), "+f"(d[15]), "+f"(d[16]), "+f"(d[17]), "+f"(d[18]), "+f"(d[19]), "+f"(d[20]), "+f"(d[21]), "+f"(d[22]), "+f"(d[23]), "+f"(d[24]), "+f"(d[25]), "+f"(d[26]), "+f"(d[27]), "+f"(d[28]), "+f"(d[29]), "+f"(d[30]), "+f"(d[31]), "+f"(d[32]), "+f"(d[33]), "+f"(d[34]), "+f"(d[35]), "+f"(d[36]), "+f"(d[37]), "+f"(d[38]), "+f"(d[39]), "+f"(d[40]), "+f"(d[41]), "+f"(d[42]), "+f"(d[43]), "+f"(d[44]), "+f"(d[45]), "+f"(d[46]), "+f"(d[47]), "+f"(d[48]), "+f"(d[49]), "+f"(d[50]), "+f"(d[51]), "+f"(d[52]), "+f"(d[53]), "+f"(d[54]), "+f"(d[55]), "+f"(d[56]), "+f"(d[57]), "+f"(d[58]), "+f"(d[59]), "+f"(d[60]), "+f"(d[61]), "+f"(d[62]), "+f"(d[63]), "+f"(d[64]), "+f"(d[65]), "+f"(d[66]), "+f"(d[67]), "+f"(d[68]), "+f"(d[69]), "+f"(d[70]), "+f"(d[71]), "+f"(d[72]), "+f"(d[73]), "+f"(d[74]), "+f"(d[75]), "+f"(d[76]), "+f"(d[77]), "+f"(d[78]), "+f"(d[79]), "+f"(d[80]), "+f"(d[81]), "+f"(d[82]), "+f"(d[83]), "+f"(d[84]), "+f"(d[85]), "+f"(d[86]), "+f"(d[87]), "+f"(d[88]), "+f"(d[89]), "+f"(d[90]), "+f"(d[91]), "+f"(d[92]), "+f"(d[93]), "+f"(d[94]), "+f"(d[95])
               : "r"(da), "r"(db), "n"(scale_d));
#undef R_
}
template <int scale_d> __device__ __forceinline__ void wgmma4_n128(float* d, uint32_t da, uint32_t db) {
#define R_ "{%0,%1,%2,%3,%4,%5,%6,%7,%8,%9,%10,%11,%12,%13,%14,%15,%16,%17,%18,%19,%20,%21,%22,%23,%24,%25,%26,%27,%28,%29,%30,%31,%32,%33,%34,%35,%36,%37,%38,%39,%40,%41,%42,%43,%44,%45,%46,%47,%48,%49,%50,%51,%52,%53,%54,%55,%56,%57,%58,%59,%60,%61,%62,%63}"
  asm volatile("{\n.reg .pred p, q;\n.reg .b64 a, b;\nsetp.ne.b32 p, %66, 0;\nsetp.eq.b32 q, 0, 0;\nmov.b64 a, {%64, 0x40000040};\nmov.b64 b, {%65, 0x40000040};\n"
               "wgmma.mma_async.sync.aligned.m64n128k16.f32.bf16.bf16 " R_ ", a, b, p, 1, 1, 0, 1;\nadd.s64 a, a, 2;\nadd.s64 b, b, 128;\n"
               "wgmma.mma_async.sync.aligned.m64n128k16.f32.bf16.bf16 " R_ ", a, b, q, 1, 1, 0, 1;\nadd.s64 a, a, 2;\nadd.s64 b, b, 128;\n"
               "wgmma.mma_async.sync.aligned.m64n128k16.f32.bf16.bf16 " R_ ", a, b, q, 1, 1, 0, 1;\nadd.s64 a, a, 2;\nadd.s64 b, b, 128;\n"
               "wgmma.mma_async.sync.aligned.m64n128k16.f32.bf16.bf16 " R_ ", a, b, q, 1, 1, 0, 1;\n}\n"
               : "+f"(d[0]), "+f"(d[1]), "+f"(d[2]), "+f"(d[3]), "+f"(d[4]), "+f"(d[5]), "+f"(d[6]), "+f"(d[7]), "+f"(d[8]), "+f"(d[9]), "+f"(d[10]), "+f"(d[11]), "+f"(d[12]), "+f"(d[13]), "+f"(d[14]), "+f"(d[15]), "+f"(d[16]), "+f"(d[17]), "+f"(d[18]), "+f"(d[19]), "+f"(d[20]), "+f"(d[21]), "+f"(d[22]), "+f"(d[23]), "+f"(d[24]), "+f"(d[25]), "+f"(d[26]), "+f"(d[27]), "+f"(d[28]), "+f"(d[29]), "+f"(d[30]), "+f"(d[31]), "+f"(d[32]), "+f"(d[33]), "+f"(d[34]), "+f"(d[35]), "+f"(d[36]), "+f"(d[37]), "+f"(d[38]), "+f"(d[39]), "+f"(d[40]), "+f"(d[41]), "+f"(d[42]), "+f"(d[43]), "+f"(d[44]), "+f"(d[45]), "+f"(d[46]), "+f"(d[47]), "+f"(d[48]), "+f"(d[49]), "+f"(d[50]), "+f"(d[51]), "+f"(d[52]), "+f"(d[53]), "+f"(d[54]), "+f"(d[55]), "+f"(d[56]), "+f"(d[57]), "+f"(d[58]), "+f"(d[59]), "+f"(d[60]), "+f"(d[61]), "+f"(d[62]), "+f"(d[63])
               : "r"(da), "r"(db), "n"(scale_d));
#undef R_
}
template <int scale_d> __device__ __forceinline__ void wgmma_n32(float* d, uint64_t descA, uint64_t descB) {
  asm volatile("{\n.reg .pred p;\nsetp.ne.b32 p, %18, 0;\n"
               "wgmma.mma_async.sync.aligned.m64n32k16.f32.bf16.bf16 {%0,%1,%2,%3,%4,%5,%6,%7,%8,%9,%10,%11,%12,%13,%14,%15}, %16, %17, p, 1, 1, 0, 1;\n}\n"
               : "+f"(d[0]), "+f"(d[1]), "+f"(d[2]), "+f"(d[3]), "+f"(d[4]), "+f"(d[5]), "+f"(d[6]), "+f"(d[7]), "+f"(d[8]), "+f"(d[9]), "+f"(d[10]), "+f"(d[11]), "+f"(d[12]), "+f"(d[13]), "+f"(d[14]), "+f"(d[15])
               : "l"(descA), "l"(descB), "n"(scale_d));
}
template <int scale_d, int tnsp_a> __device__ __forceinline__ void wgmma_n40(float* d, uint64_t descA, uint64_t descB) {
  asm volatile("{\n.reg .pred p;\nsetp.ne.b32 p, %22, 0;\n"
               "wgmma.mma_async.sync.aligned.m64n40k16.f32.bf16.bf16 {%0,%1,%2,%3,%4,%5,%6,%7,%8,%9,%10,%11,%12,%13,%14,%15,%16,%17,%18,%19}, %20, %21, p, 1, 1, %23, 1;\n}\n"
               : "+f"(d[0]), "+f"(d[1]), "+f"(d[2]), "+f"(d[3]), "+f"(d[4]), "+f"(d[5]), "+f"(d[6]), "+f"(d[7]), "+f"(d[8]), "+f"(d[9]), "+f"(d[10]), "+f"(d[11]), "+f"(d[12]), "+f"(d[13]), "+f"(d[14]), "+f"(d[15]), "+f"(d[16]), "+f"(d[17]), "+f"(d[18]), "+f"(d[19])
               : "l"(descA), "l"(descB), "n"(scale_d), "n"(tnsp_a));
}
__device__ __forceinline__ uint64_t make_desc(uint32_t addr, uint32_t lbo_bytes, uint32_t sbo_bytes) {
  return (uint64_t)((addr & 0x3FFFF) >> 4) | ((uint64_t)(lbo_bytes >> 4) << 16) | ((uint64_t)(sbo_bytes >> 4) << 32) | (1ull << 62);
}

__device__ __forceinline__ void ldsm_x4(uint32_t addr, uint32_t& r0, uint32_t& r1, uint32_t& r2, uint32_t& r3) {
  asm volatile("ldmatrix.sync.aligned.m8n8.x4.shared.b16 {%0,%1,%2,%3}, [%4];" : "=r"(r0), "=r"(r1), "=r"(r2), "=r"(r3) : "r"(addr) : "memory");
}
__device__ __forceinline__ void ldsm_x4_t(uint32_t addr, uint32_t& r0, uint32_t& r1, uint32_t& r2, uint32_t& r3) {
  asm volatile("ldmatrix.sync.aligned.m8n8.x4.trans.shared.b16 {%0,%1,%2,%3}, [%4];" : "=r"(r0), "=r"(r1), "=r"(r2), "=r"(r3) : "r"(addr) : "memory");
}
__device__ __forceinline__ void stsm_x4(uint32_t addr, uint32_t r0, uint32_t r1, uint32_t r2, uint32_t r3) {
  asm volatile("stmatrix.sync.aligned.m8n8.x4.shared.b16 [%0], {%1,%2,%3,%4};" :: "r"(addr), "r"(r0), "r"(r1), "r"(r2), "r"(r3) : "memory");
}
__device__ __forceinline__ void sts128(uint32_t addr, uint32_t a, uint32_t b, uint32_t c, uint32_t d) {
  asm volatile("st.shared.v4.u32 [%0], {%1,%2,%3,%4};" :: "r"(addr), "r"(a), "r"(b), "r"(c), "r"(d) : "memory");
}
__device__ __forceinline__ float lds32f(uint32_t addr) {
  float v;
  asm volatile("ld.shared.f32 %0, [%1];" : "=f"(v) : "r"(addr) : "memory");
  return v;
}
__device__ __forceinline__ void sts32f(uint32_t addr, float a) {
  asm volatile("st.shared.f32 [%0], %1;" :: "r"(addr), "f"(a) : "memory");
}
__device__ __forceinline__ void mma_bf16(float (&c)[4], uint32_t a0, uint32_t a1, uint32_t a2, uint32_t a3, uint32_t b0, uint32_t b1) {
  asm volatile("mma.sync.aligned.m16n8k16.row.col.f32.bf16.bf16.f32 {%0,%1,%2,%3}, {%4,%5,%6,%7}, {%8,%9}, {%0,%1,%2,%3};"
               : "+f"(c[0]), "+f"(c[1]), "+f"(c[2]), "+f"(c[3]) : "r"(a0), "r"(a1), "r"(a2), "r"(a3), "r"(b0), "r"(b1));
}
__device__ __forceinline__ uint32_t pack_bf16(float lo, float hi) {
  uint32_t r;
  asm("cvt.rn.bf16x2.f32 %0, %1, %2;" : "=r"(r) : "f"(hi), "f"(lo));
  return r;
}
__device__ __forceinline__ float bf_lo(uint32_t v) { return __uint_as_float(v << 16); }
__device__ __forceinline__ float bf_hi(uint32_t v) { return __uint_as_float(v & 0xFFFF0000u); }
__device__ __forceinline__ void split3(float x, uint32_t& h, uint32_t& m, uint32_t& l) {
  h = pack_bf16(x, 0.f); x -= bf_lo(h);
  m = pack_bf16(x, 0.f); x -= bf_lo(m);
  l = pack_bf16(x, 0.f);
}
__device__ __forceinline__ float ex2(float x) { float r; asm("ex2.approx.ftz.f32 %0, %1;" : "=f"(r) : "f"(x)); return r; }
__device__ __forceinline__ float rcp_fast(float x) { float r; asm("rcp.approx.ftz.f32 %0, %1;" : "=f"(r) : "f"(x)); return r; }
__device__ __forceinline__ void red_v4(float* p, float a, float b, float c, float d) {
  asm volatile("red.global.add.v4.f32 [%0], {%1, %2, %3, %4};" :: "l"(p), "f"(a), "f"(b), "f"(c), "f"(d) : "memory");
}
__device__ __forceinline__ uint4 ld_ll(const uint4* p) {
  uint4 v;
  asm volatile("{\n.reg .b64 a, b;\nld.relaxed.gpu.global.v2.b64 {a, b}, [%4];\nmov.b64 {%0, %1}, a;\nmov.b64 {%2, %3}, b;\n}\n"
               : "=r"(v.x), "=r"(v.y), "=r"(v.z), "=r"(v.w) : "l"(p) : "memory");
  return v;
}
__device__ __forceinline__ void st_b64(uint2* p, uint32_t a, uint32_t b) {
  asm volatile("{\n.reg .b64 v;\nmov.b64 v, {%1, %2};\nst.relaxed.gpu.global.b64 [%0], v;\n}\n" :: "l"(p), "r"(a), "r"(b) : "memory");
}
__device__ __forceinline__ void st_b128(uint4* p, uint32_t a, uint32_t b, uint32_t c, uint32_t d) {
  asm volatile("{\n.reg .b128 v;\nmov.b128 v, {%1, %2, %3, %4};\nst.relaxed.gpu.global.b128 [%0], v;\n}\n" :: "l"(p), "r"(a), "r"(b), "r"(c), "r"(d) : "memory");
}
__device__ __forceinline__ uint4 ld_b128(const uint4* p) {
  uint4 v;
  asm volatile("{\n.reg .b128 v;\nld.relaxed.gpu.global.b128 v, [%4];\nmov.b128 {%0, %1, %2, %3}, v;\n}\n" : "=r"(v.x), "=r"(v.y), "=r"(v.z), "=r"(v.w) : "l"(p) : "memory");
  return v;
}

constexpr float LOG2E = 1.4426950408889634f;

struct Params {
  const __nv_bfloat16* x0;
  const __nv_bfloat16* wA_qkv;
  const __nv_bfloat16* wA_o;
  const __nv_bfloat16* wB_qkv;
  const __nv_bfloat16* wB_phi;
  const __nv_bfloat16* wB_o;
  __nv_bfloat16* out;
};

#define ACC_DEF(d, n) _Pragma("unroll") for (int i_ = 0; i_ < (n); i_++) asm volatile("" : "=f"(d[i_]))
#define ACC_FENCE(d, n) _Pragma("unroll") for (int i_ = 0; i_ < (n); i_++) asm volatile("" : "+f"(d[i_]) :: "memory")
#define PIN(a, n) _Pragma("unroll") for (int i_ = 0; i_ < (n); i_++) asm volatile("" : "+f"((a)[i_]))
#define PINU(a, n) _Pragma("unroll") for (int i_ = 0; i_ < (n); i_++) asm volatile("" : "+r"((a)[i_]))

#define STAGE64(acc, off, p0, KIND, SEND) { \
    uint32_t w_[4][4]; \
    _Pragma("unroll") for (int j_ = 0; j_ < 4; j_++) { \
      const int o_ = (off) + j_ * 8; \
      w_[j_][0] = pack_bf16(rs0 * acc[o_ + 0], rs0 * acc[o_ + 1]); \
      w_[j_][1] = pack_bf16(rs1 * acc[o_ + 2], rs1 * acc[o_ + 3]); \
      w_[j_][2] = pack_bf16(rs0 * acc[o_ + 4], rs0 * acc[o_ + 5]); \
      w_[j_][3] = pack_bf16(rs1 * acc[o_ + 6], rs1 * acc[o_ + 7]); \
    } \
    if ((SEND) && hsend) { \
      _Pragma("unroll") for (int j_ = 0; j_ < 4; j_++) { \
        w_[j_][0] = (w_[j_][0] & ~1u) | hbit; \
        st_b128(hbase + lane + ((KIND) * 4 + j_) * 32, w_[j_][0], w_[j_][1], w_[j_][2], w_[j_][3]); \
      } \
    } \
    _Pragma("unroll") for (int j_ = 0; j_ < 4; j_++) \
      stsm_x4((KIND) ? (p0) + (j_ >> 1) * 8192 + (srowoff >> 1) + ((((uint32_t)(j_ & 1) << 5) + lhi) ^ lsw2) \
                     : (p0) + srowoff + ((((uint32_t)j_ << 5) + lhi) ^ lsw), \
              w_[j_][0], w_[j_][1], w_[j_][2], w_[j_][3]); \
  }
#define RW(j) (((j) >> 1) * 4 + ((j) & 1))
__device__ __forceinline__ float rmax16(const float* p) {
  float m[4];
#pragma unroll
  for (int j = 0; j < 4; j++) m[j] = fmaxf(fmaxf(p[RW(j)], p[RW(j + 4)]), fmaxf(p[RW(j + 8)], p[RW(j + 12)]));
  const float r = fmaxf(fmaxf(m[0], m[1]), fmaxf(m[2], m[3]));
  return fmaxf(r, __shfl_xor_sync(0xffffffffu, r, 1));
}
__device__ __forceinline__ float rmin16(const float* p) {
  float m[4];
#pragma unroll
  for (int j = 0; j < 4; j++) m[j] = fminf(fminf(p[RW(j)], p[RW(j + 4)]), fminf(p[RW(j + 8)], p[RW(j + 12)]));
  const float r = fminf(fminf(m[0], m[1]), fminf(m[2], m[3]));
  return fminf(r, __shfl_xor_sync(0xffffffffu, r, 1));
}
__device__ __forceinline__ float exps16(float* o, const float* p, float c, float b) {
  float s[4];
#pragma unroll
  for (int j = 0; j < 16; j++) { o[j] = ex2(fmaf(p[RW(j)], c, b)); if (j < 4) s[j] = o[j]; else s[j & 3] += o[j]; }
  return (s[0] + s[1]) + (s[2] + s[3]);
}
__device__ __forceinline__ void store16(const float* e, float sum, uint32_t dst, uint32_t dsw, int c0) {
  const float inv = rcp_fast(sum + __shfl_xor_sync(0xffffffffu, sum, 1));
#pragma unroll
  for (int j = 0; j < 2; j++)
    sts128(dst + (((c0 + j) << 4) ^ dsw), pack_bf16(e[j * 8] * inv, e[j * 8 + 1] * inv), pack_bf16(e[j * 8 + 2] * inv, e[j * 8 + 3] * inv),
           pack_bf16(e[j * 8 + 4] * inv, e[j * 8 + 5] * inv), pack_bf16(e[j * 8 + 6] * inv, e[j * 8 + 7] * inv));
}
__device__ __forceinline__ void expp16(uint32_t* o, const float* p, float c, float b) {
#pragma unroll
  for (int j = 0; j < 8; j++) o[j] = pack_bf16(ex2(fmaf(p[4 * j], c, b)), ex2(fmaf(p[4 * j + 1], c, b)));
}
#define SCHED_FENCE() asm volatile("pmevent 0;" ::: "memory")

__global__ void __cluster_dims__(2, 1, 1) __launch_bounds__(384, 1)
mega_kernel(const __grid_constant__ CUtensorMap tm_x0, const __grid_constant__ CUtensorMap tm_xo, const __grid_constant__ CUtensorMap tm_xb,
            const __grid_constant__ CUtensorMap tm_o, const __grid_constant__ CUtensorMap tm_wf,
            const __grid_constant__ CUtensorMap tm_wqA, const __grid_constant__ CUtensorMap tm_wqB,
            const __grid_constant__ CUtensorMap tm_woA, const __grid_constant__ CUtensorMap tm_woB,
            const __grid_constant__ CUtensorMap tm_phi, const Params prm) {
  extern __shared__ __align__(1024) uint8_t smem_raw[];
  const uint32_t sbase = smem_u32(smem_raw);
  const uint32_t bar_full = sbase + OFF_BAR;
  const uint32_t bar_done = bar_full + 384;
  const uint32_t bar_stat = bar_full + 768, bar_stat2 = bar_full + 776, bar_epi = bar_full + 784, bar_phi = bar_full + 936  ;
  const uint32_t bar_xr = bar_full + 800, bar_lx = bar_full + 808, bar_kvf = bar_full + 816  , bar_stg = bar_full + 832, bar_o1s = bar_full + 840;
  const uint32_t bar_chk = bar_full + 848;

  const int warp = __shfl_sync(0xffffffffu, threadIdx.x >> 5, 0), lane = threadIdx.x & 31;
  uint32_t rank;
  asm volatile("mov.u32 %0, %%cluster_ctarank;" : "=r"(rank));
  const int cta = (int)blockIdx.x - NAUX;
  const int cl = cta >> 1;
  const int jj = cl & 7, cc = cl >> 3;
  const int mm = cc * 2 + (int)rank;

#define LOAD_EPOCH() const unsigned epoch = ld_relaxed(&g_flags.epoch.v), ep1 = epoch + 1; (void)epoch
  int budget = 1 << 22;

  if (cta >= 0) {
    {
      const int tx = threadIdx.x;
      const __nv_bfloat16* pf = (tx < 128) ? prm.x0 + (size_t)(mm * 128 + tx) * D_MODEL + jj * 128
                                           : prm.wA_qkv + (size_t)(jj * 128 + (tx & 63)) * 3072 + ((tx - 128) >> 6) * 1024 + jj * 128 + rank * 64;
      if (tx < 320) asm volatile("prefetch.global.L2 [%0];" :: "l"(pf));
      else if (tx == 320) prefetch_tmap(&tm_x0);
      else if (tx == 352) prefetch_tmap(&tm_wqA);
      else if (tx == 383) asm volatile("prefetch.global.L2 [%0];" :: "l"(&g_flags.epoch.v));
    }
    if (elect_one()) {
#pragma unroll
      for (int i = 0; i < 4; i++) {
        const int u = warp * 4 + i;
        mbar_init(bar_full + u * 8, ((u >= 4 && u < 11) || u > 40) ? 2 : 1); mbar_init(bar_done + u * 8, 16);
      }
      mbar_init(bar_stat + warp * 16, 0x111111181182ull >> (4 * warp) & 15);
      mbar_init(bar_stat + warp * 16 + 8, 0x111111121811ull >> (4 * warp) & 15);
      asm volatile("fence.mbarrier_init.release.cluster;" ::: "memory");
    }
    __syncthreads();
    asm volatile("barrier.cluster.arrive.relaxed.aligned;" ::: "memory");
  }

  if (cta < 0) {
    LOAD_EPOCH();
    const uint32_t buf = sbase + warp * SLOT, bar = sbase + OFF_BAR + warp * 16;
    const uint32_t lsw = (lane & 7) << 4, lhi = (lane >> 4) << 4, lrow = (lane & 15) * 128;
    const bool el = elect_one();
    if (el) {
      mbar_init(bar, 1); mbar_init(bar + 8, 1);
      asm volatile("fence.mbarrier_init.release.cluster;" ::: "memory");
    }
#pragma unroll 1
    for (int rd = 0; rd < (NLAYERS > 1 ? 5 : 2); rd++) {
      if (rd >= 2 && warp >= 8) break;
      const int tk = rd < 2 ? blockIdx.x * 12 + warp : blockIdx.x * 8 + warp;
      const int half = tk & 1;
      const int blk = rd < 2 ? (tk >> 1) * 2 + rd : (rd == 2 ? 32 + (tk >> 1) : (tk >> 1) * 2 + rd - 3);
      const CUtensorMap* tm = rd < 2 ? &tm_wqA : (rd == 2 ? &tm_wqB : &tm_wf);
      const int j0 = (blk & 15) >> 1;
#define AUX_LOAD(n) { const uint32_t d_ = buf + ((n) & 1) * 8192, b_ = bar + ((n) & 1) * 8; const int r_ = kslice(j0, 2 * (n) + half) * 64; \
        mbar_expect_tx(b_, 8192); tma_load_2d(d_, tm, b_, blk * 64, r_); tma_load_2d(d_ + 4096, tm, b_, blk * 64, r_ + 32); }
      if (el) {
        if (rd == 3) { wait_flag(&g_flags.wfready[j0].v, ep1 * 16); fence_proxy_async_global(); }
        AUX_LOAD(0); AUX_LOAD(1);
      }
      __syncwarp();
      float cs[8][4];
#pragma unroll
      for (int i = 0; i < 8; i++) cs[i][0] = cs[i][1] = cs[i][2] = cs[i][3] = 0.f;
#pragma unroll 1
      for (int n = 0; n < 8; n++) {
        const uint32_t tb = buf + (n & 1) * 8192 + lrow;
        mbar_wait(bar + (n & 1) * 8, (n >> 1) & 1);
#pragma unroll
        for (int i = 0; i < 16; i++) {
          uint32_t b0, b1, b2, b3;
          ldsm_x4_t(tb + (i >> 2) * 2048 + (((i & 3) * 32 + lhi) ^ lsw), b0, b1, b2, b3);
          mma_bf16(cs[2 * (i & 3)], 0x3F803F80u, 0x3F803F80u, 0x3F803F80u, 0x3F803F80u, b0, b1);
          mma_bf16(cs[2 * (i & 3) + 1], 0x3F803F80u, 0x3F803F80u, 0x3F803F80u, 0x3F803F80u, b2, b3);
        }
        __syncwarp();
        if (el && n < 6) AUX_LOAD(n + 2);
        __syncwarp();
      }
      if (lane < 4) {
#pragma unroll
        for (int i = 0; i < 8; i++) st_b64(&g_colsum[rd >= 2][blk * 32 + i * 4 + lane][half], __float_as_uint(cs[i][0]), (__float_as_uint(cs[i][1]) & ~3u) | (ep1 & 3));
      }
      __syncwarp();
    }
  } else if (warp >= 8) {
    asm volatile("setmaxnreg.dec.sync.aligned.u32 40;");
    if (warp == 8) {
      const bool el = elect_one();
      cluster_wait();
      if (el) {
#pragma unroll 1
        for (int l = 0; l < NLAYERS; l++) {
          const uint32_t par = l & 1;
          const CUtensorMap* tqk = par ? &tm_wf : &tm_wqA;
          const CUtensorMap* tv = par ? &tm_wqB : &tm_wqA;
          const CUtensorMap* two = par ? &tm_woB : &tm_woA;
          if (l == 1) { LOAD_EPOCH(); wait_flag(&g_flags.wfready[jj].v, ep1 * 16); fence_proxy_async_global(); }
#pragma unroll 1
          for (int u = 0; u < 32; u++) {
            if (u >= 4) mbar_wait_sl(bar_done + (u - 4) * 8, par);
            else if (l) mbar_wait_sl(bar_done + (43 + u + (u >> 1)) * 8, par ^ 1);
            else if (u == 1) __nanosleep(STAG1);
            else if (u == 2) mbar_wait_sl(bar_full, 0);
            const uint32_t fb = bar_full + u * 8;
            const bool res = u < 4 ? (l || u >= 2) : (u < 11 || (u >= 18 && u < 22));
            mbar_expect_tx(fb, res ? QST : QST + SLOT);
            const int row = kslice(jj, u < 4 ? u & 1 : (u < 18 ? u - 2 : (u < 22 ? u - 6 : u - 20))) * 64 + (int)rank * 32;
            const int col = jj * 128 + (u < 4 ? u >> 1 : (u >= 18)) * 64;
            const uint32_t dst = sbase + (u & 3) * QST + rank * 4096;
            tma_load_2d_mc(dst, tqk, fb, col, row);
            tma_load_2d_mc(dst + 8192, tqk, fb, col + 1024, row);
            tma_load_2d_mc(dst + 16384, tv, fb, col + 2048, row);
            if (l == 0 && u < 4) PROFT(473 + u);
          }
#pragma unroll 1
          for (int s = 0; s < 16; s++) {
            if (s < 5) { if (s != 2 && s != 4) mbar_wait_sl(bar_done + (28 + s) * 8, par); }
            else if (s != 14) mbar_wait_sl(bar_done + (27 + s - (s == 15)) * 8, par);
            if (s == 13) mbar_wait_sl(bar_o1s, par);
            const uint32_t fb = bar_full + (32 + s) * 8;
            mbar_expect_tx(fb, (s && s < 8) ? 2 * SLOT : SLOT);
            tma_load_2d_mc(sbase + rank * 8192 + (uint32_t)((WO_BSLOT >> (4 * s)) & 15) * SLOT, two, fb, jj * 128 + (int)rank * 64, wslice(jj, s) * 64);
            if (s >= 5 && s < 8) {
              if (s == 5) { mbar_wait_sl(bar_full + 33 * 8, par); fence_proxy_async_global(); mbar_wait_sl(bar_epi, par); }
              tma_load_2d(sbase + (uint32_t)((WO_ASLOT(par) >> (4 * s)) & 15) * SLOT, &tm_o, fb, wslice(jj, s) * 64, mm * 128);
            }
          }
        }
      }
      __syncwarp();
    } else if (warp == 9) {
      const bool el = elect_one();
      if (el) {
        PROFT(472);
        tma_load_2d(sbase + OFF_S, &tm_x0, bar_full, jj * 128, mm * 128);
        __nanosleep(STAG1);
        tma_load_2d(sbase + OFF_S + SLOT, &tm_x0, bar_full + 8, jj * 128 + 64, mm * 128);
      }
      __syncwarp();
      LOAD_EPOCH();
#pragma unroll 1
      for (int lp = 0; lp < 2 * NLAYERS; lp++) {
        const int l = lp >> 1, ph = lp & 1;
        const uint32_t par = l & 1;
        const unsigned* pp = reinterpret_cast<const unsigned*>((ph ? g_obuf + 64 : g_xbuf) + (size_t)(mm * 128 + (lane >> 3) * 32 + (jj & 3) * 8) * D_MODEL + ((jj + lane + 1) & 7) * 128 + (jj >> 2) * 16);
        const CUtensorMap* tm = ph ? &tm_o : (l ? &tm_xb : &tm_x0);
        const uint32_t bit = ph ? O_BIT(l) : X_BIT(l - 1);
        const uint32_t slots = ph ? (uint32_t)(WO_ASLOT(par) >> 36) : 0x8769876u;
        uint32_t rdy = lp ? 0 : 0xFF;
        mbar_wait_sl(ph ? bar_epi : (l ? bar_done + 47 * 8 : bar_full), ph ? par : (l ? par ^ 1 : 0));
#pragma unroll 1
        for (int i = 0; i < 7; i++) {
          if (!((rdy >> i) & 1)) {
            unsigned v0 = ld_relaxed(pp);
            __nanosleep(120);
            unsigned v1 = ld_relaxed(pp);
#pragma unroll 1
            for (int it = 0; it < (1 << 18); it++) {
              uint32_t ok = __ballot_sync(0xffffffffu, ((v0 ^ bit) & 1) == 0);
              rdy = ok & (ok >> 8) & (ok >> 16) & (ok >> 24);
              if ((rdy >> i) & 1) break;
              v0 = ld_relaxed(pp);
              ok = __ballot_sync(0xffffffffu, ((v1 ^ bit) & 1) == 0);
              rdy = ok & (ok >> 8) & (ok >> 16) & (ok >> 24);
              if ((rdy >> i) & 1) break;
              v1 = ld_relaxed(pp);
            }
          }
          if (i >= (ph ? 2 : 4)) mbar_wait_sl(bar_done + (i + (ph ? 33 : 0)) * 8, par);
          if (el) {
            if (i == 0) PROFT(320 + l * 16 + ph * 2);
            mbar_expect_tx(bar_chk + i * 8, SLOT);
            tma_load_2d(sbase + ((slots >> (4 * i)) & 15) * SLOT, tm, bar_chk + i * 8, ((jj + i + 1) & 7) * 128 + ph * 64, mm * 128);
          }
          __syncwarp();
        }
        if (ph == 0 && el) {
          if (l) { wait_flag(&g_flags.xready[l][mm].v, ep1 * 8); fence_proxy_async_global(); }
#pragma unroll 1
          for (int u = 11; u < 34; u++) {
            if (u == 18) u = 22;
            mbar_wait_sl(bar_done + (u - 4) * 8, par);
            if (u == 32) mbar_expect_tx(bar_xr, 2 * SLOT);
            tma_load_2d(sbase + OFF_RA + (u & 3) * SLOT, tm, u < 32 ? bar_full + u * 8 : bar_xr, kslice(jj, u < 18 ? u - 2 : (u < 32 ? u - 20 : u - 32)) * 64, mm * 128);
            if (l == 0 && u < 16 && NLAYERS > 1) {
              if (u == 11) { mbar_expect_tx(bar_phi, SLOT + 8192); tma_load_2d(sbase + OFF_PHI, &tm_phi, bar_phi, 0, jj * 128); }
              else tma_load_2d(sbase + 12 * SLOT + (u - 12) * 4096, &tm_wqB, bar_phi, jj * 128 + ((u - 12) >> 1) * 64, mm * 64 + (u & 1) * 32);
            }
          }
          wait_flag(&g_flags.oready[l][mm].v, ep1 * 8);
          fence_proxy_async_global();
          PROFT(321 + l * 16);
#pragma unroll 1
          for (int s = 1; s < 5; s++) {
            if (s != 3) mbar_wait_sl(s == 2 ? bar_lx : bar_done + (s == 1 ? 30 : 31 + par) * 8, par);
            tma_load_2d(sbase + (uint32_t)((WO_ASLOT(par) >> (4 * s)) & 15) * SLOT, &tm_o, bar_full + (32 + s) * 8, wslice(jj, s) * 64, mm * 128);
          }
        }
        __syncwarp();
      }
      cluster_wait();
    } else {
      const int hw = warp - 10;
      LOAD_EPOCH();
      const bool el = elect_one();
      cluster_wait();
      if (hw == 0) {
        mbar_wait_sl(bar_full + 8, 0);
        if (lane < 7) prefetch_tmap(lane == 0 ? &tm_xb : lane == 1 ? &tm_o : lane == 2 ? &tm_wf : lane == 3 ? &tm_wqB : lane == 4 ? &tm_woA : lane == 5 ? &tm_woB : &tm_phi);
        if (lane < 4) asm volatile("prefetch.global.L2 [%0];" :: "l"(prm.wB_phi + jj * 4096 + mm * 256 + lane * 64));
#pragma unroll 1
        for (int i = 0; i < 8; i++) {
          asm volatile("prefetch.global.L2 [%0];" :: "l"(prm.wB_qkv + (size_t)(mm * 64 + (i & 3) * 16 + (lane >> 1)) * 3072 + (i >> 2) * 1024 + jj * 128 + (lane & 1) * 64));
          __nanosleep(PFGAP);
        }
      } else {
#pragma unroll 1
        for (int b = 0; b < 2; b++) {
          float4* z = reinterpret_cast<float4*>(g_kv[b] + (jj * 4) * KVH + mm * (4 * KVH / 16)) + lane;
#pragma unroll
          for (int i = 0; i < 5; i++) z[i * 32] = make_float4(0.f, 0.f, 0.f, 0.f);
        }
      }
      __syncwarp();
      uint32_t chkp = 0;
#pragma unroll 1
      for (int lp = 0; lp < 2 * NLAYERS; lp++) {
        const int l = lp >> 1, ph = lp & 1;
        const uint32_t par = l & 1;
        int lane; asm volatile("mov.u32 %0, %%laneid;" : "=r"(lane));
        if (hw) {
          const CUtensorMap* tm = ph ? &tm_o : &tm_xb;
          const uint32_t bit = ph ? O_BIT(l) : X_BIT(l - 1);
          const uint32_t slots = ph ? (uint32_t)(WO_ASLOT(par) >> 36) : 0x8769876u;
#pragma unroll 1
          for (int c = 0; c < 7; c++) {
            const uint32_t tile = sbase + ((slots >> (4 * c)) & 15) * SLOT;
#pragma unroll 1
            for (int it = 0; it < (1 << 12); it++) {
              mbar_wait_sl(bar_chk + c * 8, (chkp >> c) & 1);
              chkp ^= 1u << c;
              if (el && c == 0) PROFT(488 + lp);
              if (lp == 0) break;
              uint32_t a1 = 1, o1 = 0;
#pragma unroll
              for (int i = 0; i < 16; i++) {
                uint32_t w;
                asm volatile("ld.shared.u32 %0, [%1];" : "=r"(w) : "r"(tile + i * 1024 + (lane & 7) * 132 + (lane >> 3) * 32) : "memory");
                a1 &= w; o1 |= w;
              }
              if (__all_sync(0xffffffffu, ((bit ? a1 : ~o1) & 1) != 0)) break;
              if (el) {
                fence_proxy_async_smem();
                mbar_expect_tx(bar_chk + c * 8, SLOT);
                tma_load_2d(tile, tm, bar_chk + c * 8, ((jj + c + 1) & 7) * 128 + ph * 64, mm * 128);
                RETRY_COUNT();
              }
              __syncwarp();
            }
            if (el) mbar_arrive_local(bar_full + (c + (ph ? 41 : 4)) * 8);
            __syncwarp();
          }
          if (ph) continue;
#pragma unroll 1
          for (int hp = 0; hp < 2; hp++) {
            const uint4* src = reinterpret_cast<const uint4*>(g_colsum[par][jj * 64 + hp * 32 + lane]);
            uint32_t bad;
            int it = 0;
            float c[6];
            do {
              bad = 0;
#pragma unroll
              for (int p = 0; p < 3; p++) {
                const uint4 v = ld_ll(src + p * 512);
                bad |= (v.y ^ ep1) | (v.w ^ ep1);
                c[2 * p] = __uint_as_float(v.x) + __uint_as_float(v.z); c[2 * p + 1] = __uint_as_float(v.y) + __uint_as_float(v.w);
              }
              bad &= 3;
              if (bad) __nanosleep(300);
            } while (bad && ++it < (1 << 16));
#pragma unroll
            for (int p = 0; p < 6; p++) {
              uint32_t h, m, lo;
              split3(c[p], h, m, lo);
              sts128(sbase + OFF_LNB + hp * 4096 + (p >> 1) * 1024 + lane * 32 + (p & 1) * 16, h | (m << 16), h | (lo << 16), h | (m << 16), lo | (m << 16));
            }
            fence_proxy_async_smem();
            __syncwarp();
            if (el) { mbar_arrive_local(hp ? bar_stat2 : bar_stat); if (hp == 0) PROFT(324 + l * 16); }
            __syncwarp();
          }
        } else if (ph == 0) {
          mbar_wait_sl(bar_done + 24, par);
          const uint4* sp = reinterpret_cast<const uint4*>(g_stats + (size_t)(mm * 128) * 8) + lane;
#pragma unroll 1
          for (int hf = 0; hf < 4; hf++) {
            uint4 v[4];
            uint32_t bad;
            int it = 0;
            do {
              bad = 0;
#pragma unroll
              for (int i = 0; i < 4; i++) { v[i] = ld_ll(sp + (hf * 4 + i) * 32); bad |= (v[i].y ^ STAT_TAG(l)) | (v[i].w ^ STAT_TAG(l)); }
              bad &= 3;
              if (bad) __nanosleep(200);
            } while (bad && ++it < (1 << 16));
            __syncwarp();
            float mean = 0.f, m2 = 0.f;
#pragma unroll
            for (int i = 0; i < 4; i++) {
              float a = __uint_as_float(v[i].x) + __uint_as_float(v[i].z);
              a += __shfl_xor_sync(0xffffffffu, a, 1); a += __shfl_xor_sync(0xffffffffu, a, 2);
              a *= 0.125f;
              const float e0 = __uint_as_float(v[i].x) - a, e1 = __uint_as_float(v[i].z) - a;
              float q = fmaf(fmaf(e0, e0, e1 * e1), 128.f, __uint_as_float(v[i].y) + __uint_as_float(v[i].w));
              q += __shfl_xor_sync(0xffffffffu, q, 1); q += __shfl_xor_sync(0xffffffffu, q, 2);
              if ((lane & 3) == i) { mean = a; m2 = q; }
            }
            const uint32_t row = hf * 32 + (lane & 3) * 8 + (lane >> 2);
            uint32_t h, m, lo;
            split3(-0.5f * mean, h, m, lo);
            sts128(sbase + OFF_LNA + row * 16, h | (h << 16), m | (h << 16), lo | (m << 16), m | (lo << 16));
            sts32f(sbase + OFF_ST + row * 4, rsqrtf(m2 * (1.f / 1024.f) + 1e-5f));
          }
          fence_proxy_async_smem();
          __syncwarp();
          if (el) { mbar_arrive_local(bar_stat); PROFT(323 + l * 16); }
          __syncwarp();
#pragma unroll 1
          for (int i = 0; i < 8 - 4 * l; i++) {
            asm volatile("prefetch.global.L2 [%0];" :: "l"(i < 4 ? (l ? prm.wB_o : prm.wA_o) + (size_t)cta * 8192 + i * 2048 + lane * 64
                                                                 : prm.wB_qkv + (size_t)(cta * 8 + (i - 4) * 2 + (lane >> 4)) * 3072 + 2048 + (lane & 15) * 64));
            __nanosleep(PFGAP);
          }
          continue;
        }
        if (hw) {
          if (l & 1) {
#pragma unroll 1
            for (int h = 0; h < 2; h++) {
              asm volatile("bar.sync %0, 288;" :: "r"(BAR_KV + h) : "memory");
              __syncwarp();
              PROFT(331 + l * 16 + h);
              if (lane < 16) signal_release(&g_flags.kvready[(l & 2) + h][jj][lane].v);
              const unsigned* kf = &g_flags.kvready[(l & 2) + h][jj][mm].v;
              unsigned v0 = ld_relaxed(kf);
              __nanosleep(150);
              unsigned v1 = ld_relaxed(kf);
#pragma unroll 1
              for (int it = 0; it < (1 << 18); it++) {
                if (v0 == ep1 * 16) break;
                v0 = ld_relaxed(kf);
                if (v1 == ep1 * 16) break;
                v1 = ld_relaxed(kf);
              }
              fence_acquire();
              __syncwarp();
              if (el) { mbar_arrive_local(bar_kvf + h * 8); PROFT(333 + l * 16 + h); }
              __syncwarp();
            }
          }
        } else {
#pragma unroll 1
          for (uint32_t ev = (l == 0 && NLAYERS > 1) ? 0x83216054u : 0x83210u; ev != 8; ev >>= 4) {
            const int e = ev & 15;
            asm volatile("bar.sync %0, 288;" :: "r"((0xFECA987 >> (4 * e)) & 15) : "memory");
            if (el) {
              if (e < 4) {
                PROFT(325 + l * 16 + e);
                tma_store_2d((e & 2) ? (l < NLAYERS - 1 ? &tm_xb : &tm_xo) : &tm_o, sbase + ((0xBA3C >> (4 * e)) & 15) * SLOT, jj * 128 + (e & 1) * 64, mm * 128);
              } else {
                if (e == 5) mbar_expect_tx(bar_phi + 8, SLOT);
#pragma unroll 1
                for (int i = 0; i < 4; i++) {
                  const uint32_t a = sbase + (e > 4 ? 10 : 12) * SLOT + i * 4096;
                  const int c0 = (e > 4 ? 1024 : 0) + jj * 128 + (i >> 1) * 64, c1 = mm * 64 + (i & 1) * 32;
                  if (e == 5) tma_load_2d(a, &tm_wqB, bar_phi + 8, c0, c1); else tma_store_2d(&tm_wf, a, c0, c1);
                }
                if (e != 5) {
                  asm volatile("cp.async.bulk.commit_group;\ncp.async.bulk.wait_group.read 0;" ::: "memory");
                  mbar_arrive_local(bar_phi + (e - 4) * 4);
                }
              }
              if ((0x4B >> e) & 1) bulk_commit_wait();
              if (e == 1 || e == 3) PROFT(480 + l * 2 + (e >> 1));
              if (e == 1) { mbar_arrive_remote(bar_o1s, 0); mbar_arrive_remote(bar_o1s, 1); }
              else if (e == 0 || e == 6 || (e == 3 && l < NLAYERS - 1)) signal_release(e == 0 ? &g_flags.oready[l][mm].v : e == 6 ? &g_flags.wfready[jj].v : &g_flags.xready[l + 1][mm].v);
              if (e == 1 || e == 3) PROFT(329 + l * 16 + (e >> 1));
              if (e == 6) PROFT(335);
            }
            __syncwarp();
          }
        }
      }
    }
    cluster_sync();
  } else {
    asm volatile("setmaxnreg.inc.sync.aligned.u32 232;");
    LOAD_EPOCH();
    const int wg = warp >> 2;
    const int r0 = warp * 16;
    const uint32_t pK = sbase + OFF_S, pV = sbase + OFF_S + SLOT;
#define PMASKS(on, bit) const uint32_t pm0 = ((on) && t == (g & 3) && (g >> 2) == (g & 1)), pm1 = ((on) && t == (g & 3) && (g >> 2) != (g & 1)), pbit = (bit)
#define PBIT0(w) (((w) & ~pm0) | (pbit & pm0))
#define PBIT1(w) (((w) & ~pm1) | (pbit & pm1))
#define LANE_CONSTS() \
    int lane; asm volatile("mov.u32 %0, %%laneid;" : "=r"(lane)); \
    const int g = lane >> 2, t = lane & 3; \
    const uint32_t srowoff = (r0 + (lane & 15)) * 128, lsw = (lane & 7) << 4, lhi = (lane >> 4) << 4, lsw2 = (lane & 6) << 3; \
    (void)g; (void)t; (void)srowoff; (void)lsw; (void)lhi; (void)lsw2;
    uint32_t stgp = 0, peer;
    asm volatile("mapa.shared::cluster.u32 %0, %1, %2;" : "=r"(peer) : "r"(sbase), "r"(rank ^ 1));
    peer -= sbase;
    const uint32_t dA0 = (((sbase & 0x3FFFF) + wg * 8192) >> 4) | 0x10000u, dB0 = ((sbase & 0x3FFFF) >> 4) | 0x2000000u;
    cluster_wait();
#define STG_ARRIVE() { __syncwarp(); if (elect_one()) mbar_arrive_local(bar_stg); }
#define STG_WAIT() { mbar_wait(bar_stg, stgp); stgp ^= 1; }
#define PROFS() do {} while (0)
#define REL(addr) { if (elect_one()) { mbar_arrive_local(addr); asm volatile("mbarrier.arrive.shared::cluster.b64 _, [%0];" :: "r"((addr) + peer) : "memory"); } }
#define QSTEP(ACC, DA, SC, PRE) { \
      const uint32_t da = (DA), db = dB0 + (ub & 0x18) * (QST >> 7); \
      mbar_wait(ub, par); \
      PRE; \
      wgmma_fence(); \
      wgmma4_n192<SC>(ACC, da, db); \
      wgmma_commit(); PROFS(); }
#define QREL() { wgmma_wait<1>(); REL(ub + 376); ub += 8; }
#define RA_CUR (dA0 + (OFF_RA >> 4) + (ub & 0x18) * (SLOT >> 7))
#define PUMP1() { QSTEP(S1, RA_CUR, 1, {}); QREL(); }
#define PUMP0() { PUMP1(); SCHED_FENCE(); }
#define PUMP() if (h == 0) PUMP1()
#define WSTEP() { \
      const uint32_t s4 = (ub - bar_full - 256) >> 1; \
      const uint32_t da = dA0 + (((uint32_t)(WO_ASLOT(par) >> s4) & 15) << 10), db = dB0 + (((uint32_t)(WO_BSLOT >> s4) & 15) << 10); \
      mbar_wait(ub, par); \
      wgmma_fence(); \
      wgmma4_n128<1>(S1, da, db); \
      wgmma_commit(); PROFS(); \
      wgmma_wait<1>(); \
      if (s4 > par * 4) REL(ub + 376); \
      ub += 8; }
#define PUMPS(n) { _Pragma("unroll 1") for (int i_ = 0; i_ < (n); i_++) PUMP1(); }
#define SITE(n) { if ((BMASK >> (n)) & 1) { PUMP(); } else SCHED_FENCE(); }
#define LNSTEP(ACC, hh) { wgmma_fence(); wgmma_n192<1, 0>(ACC, make_desc(sbase + OFF_LNA + wg * 1024, 0, 128) ^ (1ull << 62), make_desc(sbase + OFF_LNB + (hh) * 4096, 0, 128) ^ (1ull << 62)); }
#define DRAIN_A(ACC, PMP) { \
      LANE_CONSTS(); \
      STAGE64(ACC, 64, pV, 1, 1); \
      PMP; \
      STAGE64(ACC, 32, pK, 0, 1); \
      STG_ARRIVE(); \
      _Pragma("unroll") for (int i_ = 0; i_ < 16; i_++) qa[i_] = pack_bf16(ACC[2 * i_], ACC[2 * i_ + 1]); \
      PINU(qa, 16); }
#define DRAIN_B(ACC) { \
      LANE_CONSTS(); \
      STAGE64(ACC, 64, pV, 1, 0); \
      _Pragma("unroll") for (int i_ = 0; i_ < 64; i_++) st[i_] = ACC[i_]; \
      PIN(st, 64); }
#define PUBLISH_O() { fence_proxy_async_smem(); asm volatile("bar.arrive %0, 288;" :: "r"(BAR_O + h) : "memory"); }
#define REST_P1(SKEW) { \
      mbar_wait(bar_stat2, par); \
      LNSTEP(S1, 1); \
      _Pragma("unroll 1") while (ub < bar_full + 256) { \
        if (ub == bar_full + 256 - 8 * (SKEW) && wg == 0) bar_sync<BAR_SKEW, 256>(); \
        QSTEP(S1, RA_CUR, 1, {}); \
        if (ub == bar_full + 248 && wg == 1) bar_arrive<BAR_SKEW, 256>(); \
        QREL(); \
      } \
      hbase += 256; \
      mbar_wait(bar_done + (31 - (SKEW)) * 8, par);        \
      wgmma_wait<0>(); \
      ACC_FENCE(S1, 96); \
      REL(bar_done + 31 * 8); \
      PROF(13); }
#define KV_LOAD(v, hh) { \
          const float4* kvg_ = reinterpret_cast<const float4*>(g_kv[l >> 1] + (jj * 4 + (hh) * 2 + wg) * KVH) + (warp & 3) * 32 + lane; \
          mbar_wait(bar_kvf + (hh) * 8, l >> 1); \
          _Pragma("unroll") for (int i = 0; i < 5; i++) { const float4 q_ = __ldcg(kvg_ + i * 128); (v)[i * 4] = q_.x; (v)[i * 4 + 1] = q_.y; (v)[i * 4 + 2] = q_.z; (v)[i * 4 + 3] = q_.w; } }
#define KV_TILE(v, pT) { \
          const uint32_t kd = (pT) + wg * 8192 + ((warp & 3) * 16 + (lane & 15)) * 128; \
          _Pragma("unroll") for (int i = 0; i < 2; i++) \
            stsm_x4(kd + ((i * 32 + lhi) ^ lsw), pack_bf16((v)[i * 8], (v)[i * 8 + 1]), pack_bf16((v)[i * 8 + 2], (v)[i * 8 + 3]), pack_bf16((v)[i * 8 + 4], (v)[i * 8 + 5]), pack_bf16((v)[i * 8 + 6], (v)[i * 8 + 7])); \
          stsm_x4(kd + ((64u + lhi) ^ lsw), pack_bf16((v)[16], 1.f), pack_bf16((v)[18], 1.f), 0u, 0u); }
#define O_MMA(o, pA, pB, pT) { \
          _Pragma("unroll") for (int hh = 0; hh < 2; hh++) { \
            const uint64_t da = make_desc((hh ? (pB) : (pA)) + wg * 8192, 16, 1024), db = make_desc((pT) + hh * 8192, 16, 1024); \
            _Pragma("unroll") for (int ks = 0; ks < 4; ks += 2) { \
              wgmma_n40<0, 0>((o) + hh * 48 + ks * 12, da + ks * 2, db + ks * 128); wgmma_n40<1, 0>((o) + hh * 48 + ks * 12, da + ks * 2 + 2, db + ks * 128 + 128); } \
          } \
          wgmma_commit(); }
#define O_OUT(o, pA, hp) { \
          bar_wg(wg);            \
          PMASKS(hp, O_BIT(l)); \
          _Pragma("unroll") for (int hh = 0; hh < 2; hh++) { \
            const float* x = (o) + hh * 48; \
            const float* y = x + 24; \
            const float rx0 = rcp_fast(x[17]), ry0 = rcp_fast(y[17]), rx1 = rcp_fast(x[19]), ry1 = rcp_fast(y[19]); \
            const float i0 = rcp_fast(fmaf(x[16], rx0, y[16] * ry0) + 1e-6f), i1 = rcp_fast(fmaf(x[18], rx1, y[18] * ry1) + 1e-6f); \
            const float ax0 = rx0 * i0, ay0 = ry0 * i0, ax1 = rx1 * i1, ay1 = ry1 * i1; \
            _Pragma("unroll") for (int dp = 0; dp < 2; dp++) \
              stsm_x4((pA) + srowoff + ((hh * 64 + dp * 32 + lhi) ^ lsw), \
                      PBIT0(pack_bf16(fmaf(x[dp * 8], ax0, y[dp * 8] * ay0), fmaf(x[dp * 8 + 1], ax0, y[dp * 8 + 1] * ay0))), \
                      PBIT0(pack_bf16(fmaf(x[dp * 8 + 2], ax1, y[dp * 8 + 2] * ay1), fmaf(x[dp * 8 + 3], ax1, y[dp * 8 + 3] * ay1))), \
                      PBIT1(pack_bf16(fmaf(x[dp * 8 + 4], ax0, y[dp * 8 + 4] * ay0), fmaf(x[dp * 8 + 5], ax0, y[dp * 8 + 5] * ay0))), \
                      PBIT1(pack_bf16(fmaf(x[dp * 8 + 6], ax1, y[dp * 8 + 6] * ay1), fmaf(x[dp * 8 + 7], ax1, y[dp * 8 + 7] * ay1)))); \
          } \
          fence_proxy_async_smem(); \
          bar_arrive<BAR_O + (hp), 288>(); }
#define FOLD(tile, rd) { \
          LANE_CONSTS(); \
          float d[32]; \
          ACC_DEF(d, 32); \
          mbar_wait(bar_phi + (rd) * 8, 0); \
          wgmma_fence(); \
          _Pragma("unroll") for (int i = 0; i < 2; i++) { \
            const uint64_t da = make_desc((tile) + wg * 8192 + i * 64, 16, 1024); \
            const uint64_t db = make_desc(sbase + OFF_PHI + wg * 4096 + i * 2048, 16, 512) ^ (3ull << 62); \
            wgmma_n32<0>(d + i * 16, da, db); wgmma_n32<1>(d + i * 16, da + 2, db + 64); \
          } \
          wgmma_commit(); \
          PUMP0(); \
          ACC_FENCE(d, 32); \
          bar_wg(wg); \
          _Pragma("unroll") for (int i = 0; i < 4; i++) { \
            const float* x = d + (i & 1) * 8 + (i >> 1) * 2; \
            sts128((tile) + wg * 8192 + ((warp & 3) * 16 + (i >> 1) * 8 + g) * 128 + (((2 * t + (i & 1)) ^ g) << 4), \
                   pack_bf16(x[0], x[1]), pack_bf16(x[4], x[5]), pack_bf16(x[16], x[17]), pack_bf16(x[20], x[21])); \
          } \
          fence_proxy_async_smem(); \
          bar_arrive<BAR_WF + 3 * (rd), 288>(); }
#define LOAD_X0(base) \
      _Pragma("unroll") for (int j = 0; j < 8; j++) { \
        uint32_t x0, x1, x2, x3; \
        ldsm_x4((base) + (j >> 2) * SLOT + srowoff + ((((uint32_t)(j & 3) << 5) + lhi) ^ lsw), x0, x1, x2, x3); \
        S1[j * 8 + 0] = bf_lo(x0); S1[j * 8 + 1] = bf_hi(x0); S1[j * 8 + 2] = bf_lo(x1); S1[j * 8 + 3] = bf_hi(x1); \
        S1[j * 8 + 4] = bf_lo(x2); S1[j * 8 + 5] = bf_hi(x2); S1[j * 8 + 6] = bf_lo(x3); S1[j * 8 + 7] = bf_hi(x3); \
      }
#define LOAD_X() { \
      wgmma_wait<0>(); \
      mbar_wait(bar_xr, par); \
      LOAD_X0(sbase + OFF_RA); \
      ACC_FENCE(S1, 64); \
      __syncwarp(); if (elect_one()) mbar_arrive_local(bar_lx); }

    float S1[96];
#pragma unroll
    for (int i = 0; i < 64; i++) S1[i] = 0.f;
#pragma unroll 1
    for (int l = 0; l < NLAYERS; l++) {
      const uint32_t par = l & 1;
      bar_wg(wg);
      PROF(0);
      uint32_t ub = bar_full;
      const bool hsend = (warp == 7) && (mm < 15);
      const uint32_t hbit = (NLAYERS > 2) ? (l == 0) : (ep1 & 1);
      float S0[96];
      {
        LANE_CONSTS();
        ACC_DEF(S0, 96);
        QSTEP(S0, dA0 + (OFF_S >> 4), 0, {});
        ub += 8;
        PROF(1);
        if (l == 0) { mbar_wait(ub, 0); LOAD_X0(pK); }
        SCHED_FENCE();
        {
          float a0 = S1[0], a1 = S1[2], b0 = S1[1], b1 = S1[3];
#pragma unroll
          for (int i = 4; i < 64; i += 4) { a0 += S1[i]; b0 += S1[i + 1]; a1 += S1[i + 2]; b1 += S1[i + 3]; }
          a0 += b0; a1 += b1;
          a0 += __shfl_xor_sync(0xffffffffu, a0, 1); a1 += __shfl_xor_sync(0xffffffffu, a1, 1);
          a0 += __shfl_xor_sync(0xffffffffu, a0, 2); a1 += __shfl_xor_sync(0xffffffffu, a1, 2);
          a0 *= (1.f / 128.f); a1 *= (1.f / 128.f);
          asm volatile("" : "+f"(a0), "+f"(a1));
          QSTEP(S0, dA0 + ((OFF_S + SLOT) >> 4), 1, wgmma_wait<0>());
          REL(ub + 376); ub += 8;
          SCHED_FENCE();
          float q0 = 0.f, q1 = 0.f;
          b0 = 0.f; b1 = 0.f;
#pragma unroll
          for (int i = 0; i < 64; i += 4) {
            const float d0 = S1[i] - a0, d1 = S1[i + 1] - a0, d2 = S1[i + 2] - a1, d3 = S1[i + 3] - a1;
            q0 = fmaf(d0, d0, q0); b0 = fmaf(d1, d1, b0); q1 = fmaf(d2, d2, q1); b1 = fmaf(d3, d3, b1);
          }
          q0 += b0; q1 += b1;
          q0 += __shfl_xor_sync(0xffffffffu, q0, 1); q1 += __shfl_xor_sync(0xffffffffu, q1, 1);
          q0 += __shfl_xor_sync(0xffffffffu, q0, 2); q1 += __shfl_xor_sync(0xffffffffu, q1, 2);
          if (t < 2) st_b64(g_stats + (size_t)(mm * 128 + r0 + g + t * 8) * 8 + jj, __float_as_uint(t ? a1 : a0), (__float_as_uint(t ? q1 : q0) & ~3u) | STAT_TAG(l));
        }
        ACC_DEF(S1, 96);
        QSTEP(S1, dA0 + (OFF_S >> 4), 0, {});
        QREL();
        QSTEP(S1, dA0 + ((OFF_S + SLOT) >> 4), 1, {});
        QREL();
#pragma unroll 1
        for (int i = 0; i < 14; i++) {
          QSTEP(S0, RA_CUR, 1, {});
          if (i == 0) PROF(2);
          QREL();
        }
      }
      LANE_CONSTS();
      uint4* hbase = g_halo + (size_t)(mm * 8 + jj) * 512;
      mbar_wait(bar_stat, par);
      LNSTEP(S0, 0);
      wgmma_commit();
      const float rs0 = lds32f(sbase + OFF_ST + (r0 + g) * 4), rs1 = lds32f(sbase + OFF_ST + (r0 + g + 8) * 4);
      PUMP0();
      ACC_FENCE(S0, 96);
      PROF(3);
      if (!par) {
        constexpr uint32_t par = 0;
        uint32_t qa[16];
        DRAIN_A(S0, PUMP0());
#pragma unroll 1
        for (int h = 0; h < 2; h++) {
          const uint32_t pO = sbase + (h ? 3 : 12) * SLOT;
          PROF(4 + h * 12);
          const bool fold = (l == 0 && h == 0 && NLAYERS > 1);
          if (fold) FOLD(pO, 0) else if (h == 0) PUMPS(HPUMP1);
          LANE_CONSTS();
          uint4 hv[8];
#pragma unroll
          for (int i = 0; i < 8; i++) hv[i] = make_uint4(hbit, 0, 0, 0);
          const bool hrec = (warp == 0 && mm > 0);
          if (hrec) {
#pragma unroll
            for (int i = 0; i < 8; i++) hv[i] = ld_b128(hbase + lane - 8 * 512 + i * 32);
          }
          if (h) LOAD_X() else PUMPS(HPUMP2);
          const uint32_t halo = sbase + OFF_HALO;
          STG_WAIT();
          if (warp == 0) {
#pragma unroll 1
            for (int it = 0; it < (1 << 16); it++) {
              uint32_t bad = 0;
#pragma unroll
              for (int i = 0; i < 8; i++) bad |= hv[i].x ^ hbit;
              if (__all_sync(0xffffffffu, (bad & 1) == 0)) break;
#pragma unroll
              for (int i = 0; i < 8; i++) hv[i] = ld_b128(hbase + lane - 8 * 512 + i * 32);
            }
#pragma unroll
            for (int i = 0; i < 8; i++)
              stsm_x4(i < 4 ? halo + srowoff + ((((uint32_t)i << 5) + lhi) ^ lsw)
                            : halo + (srowoff >> 1) + (i >> 1) * 1024 + ((((uint32_t)(i & 1) << 5) + lhi) ^ lsw2), hv[i].x, hv[i].y, hv[i].z, hv[i].w);
            __syncwarp();
          }
          PROF(5 + h * 12);
          const uint32_t kb1 = pK + r0 * 128, vb1 = pV + r0 * 64;
          const uint32_t kb0 = r0 ? kb1 - 2048 : halo, vb0 = r0 ? vb1 - 1024 : halo + 2048;
          const uint32_t vhs = r0 ? 8192 : 1024;
          float s[2][4][4];
          {
            uint32_t kf[2][4][4];
#pragma unroll
            for (int i = 0; i < 8; i++) {
              const int hh = i >> 2, jb = i & 3;
              ldsm_x4(((jb < 2) ? kb0 : kb1) + ((jb & 1) * 8 + (lane & 7)) * 128 + ((hh * 64 + ((lane >> 3) << 4)) ^ lsw), kf[hh][jb][0], kf[hh][jb][1], kf[hh][jb][2], kf[hh][jb][3]);
              s[hh][jb][0] = s[hh][jb][1] = s[hh][jb][2] = s[hh][jb][3] = 0.f;
            }
#pragma unroll
            for (int ks = 0; ks < 2; ks++)
#pragma unroll
              for (int i = 0; i < 8; i++) {
                const int hh = i >> 2, jb = i & 3;
                mma_bf16(s[hh][jb], qa[hh * 8 + ks * 4], qa[hh * 8 + ks * 4 + 1], qa[hh * 8 + ks * 4 + 2], qa[hh * 8 + ks * 4 + 3], kf[hh][jb][ks * 2], kf[hh][jb][ks * 2 + 1]);
              }
          }
          PUMP();
          if (fold) bar_arrive<BAR_WF + 2, 288>();
          PROF(6 + h * 12);
          const bool e = g & 1, hb = (2 * t + (g & 1)) <= g;
          uint32_t vf[2][2][2][4];
#pragma unroll
          for (int i = 0; i < 8; i++) {
            const int hh = i >> 2, ks = (i >> 1) & 1, dp = i & 1;
            ldsm_x4_t((ks ? vb1 + hh * 8192 : vb0 + hh * vhs) + (lane & 15) * 64 + ((dp * 32 + lhi) ^ lsw2), vf[hh][ks][dp][0], vf[hh][ks][dp][1], vf[hh][ks][dp][2], vf[hh][ks][dp][3]);
          }
          float va[2][2], vb[2][2], mx[2][2];
#pragma unroll
          for (int hh = 0; hh < 2; hh++) {
            va[hh][0] = e ? s[hh][1][1] : s[hh][1][0];
            vb[hh][0] = hb ? (e ? s[hh][2][1] : s[hh][2][0]) : (e ? s[hh][0][1] : s[hh][0][0]);
            va[hh][1] = e ? s[hh][2][3] : s[hh][2][2];
            vb[hh][1] = hb ? (e ? s[hh][3][3] : s[hh][3][2]) : (e ? s[hh][1][3] : s[hh][1][2]);
          }
          if (warp == 0 && mm == 0) {
#pragma unroll
            for (int hh = 0; hh < 2; hh++) { va[hh][0] = -INFINITY; if (!hb) { vb[hh][0] = -INFINITY; vb[hh][1] = -INFINITY; } }
          }
#pragma unroll
          for (int i = 0; i < 4; i++) mx[i >> 1][i & 1] = fmaxf(va[i >> 1][i & 1], vb[i >> 1][i & 1]);
#pragma unroll
          for (int o = 1; o <= 2; o <<= 1)
#pragma unroll
            for (int i = 0; i < 4; i++) mx[i >> 1][i & 1] = fmaxf(mx[i >> 1][i & 1], __shfl_xor_sync(0xffffffffu, mx[i >> 1][i & 1], o));
          const float sc0 = rs0 * (0.17677669529663687f * LOG2E), sc1 = rs1 * (0.17677669529663687f * LOG2E);
#pragma unroll
          for (int i = 0; i < 4; i++) {
            const float sc = (i & 1) ? sc1 : sc0, m = mx[i >> 1][i & 1];
            va[i >> 1][i & 1] = ex2((va[i >> 1][i & 1] - m) * sc); vb[i >> 1][i & 1] = ex2((vb[i >> 1][i & 1] - m) * sc);
            mx[i >> 1][i & 1] = va[i >> 1][i & 1] + vb[i >> 1][i & 1];
          }
          if (h == 0 && ASITE) { PIN(&va[0][0], 4); PIN(&vb[0][0], 4); PIN(&mx[0][0], 4); PUMP1(); }
#pragma unroll
          for (int o = 1; o <= 2; o <<= 1)
#pragma unroll
            for (int i = 0; i < 4; i++) mx[i >> 1][i & 1] += __shfl_xor_sync(0xffffffffu, mx[i >> 1][i & 1], o);
          const uint32_t selA = e ? 0x1044 : 0x4410, selB = e ? 0x3244 : 0x4432, selL = hb ? 0x4444 : selB, selH = hb ? selB : 0x4444;
          float o[2][4][4];
          uint32_t pa[2][6];
#pragma unroll
          for (int hh = 0; hh < 2; hh++) {
            const float i0 = rcp_fast(mx[hh][0]), i1 = rcp_fast(mx[hh][1]);
            const uint32_t w0 = pack_bf16(va[hh][0] * i0, vb[hh][0] * i0), w1 = pack_bf16(va[hh][1] * i1, vb[hh][1] * i1);
            pa[hh][0] = __byte_perm(w0, 0, selL); pa[hh][1] = __byte_perm(w0, 0, selA); pa[hh][2] = __byte_perm(w1, 0, selL);
            pa[hh][3] = __byte_perm(w0, 0, selH); pa[hh][4] = __byte_perm(w1, 0, selA); pa[hh][5] = __byte_perm(w1, 0, selH);
#pragma unroll
            for (int dj = 0; dj < 4; dj++) { o[hh][dj][0] = o[hh][dj][1] = o[hh][dj][2] = o[hh][dj][3] = 0.f; }
          }
          PROF(7 + h * 12);
#pragma unroll
          for (int i = 0; i < 8; i++) mma_bf16(o[i >> 2][i & 3], pa[i >> 2][0], 0u, pa[i >> 2][1], pa[i >> 2][2], vf[i >> 2][0][(i >> 1) & 1][(i & 1) * 2], vf[i >> 2][0][(i >> 1) & 1][(i & 1) * 2 + 1]);
#pragma unroll
          for (int i = 0; i < 8; i++) mma_bf16(o[i >> 2][i & 3], pa[i >> 2][3], pa[i >> 2][4], 0u, pa[i >> 2][5], vf[i >> 2][1][(i >> 1) & 1][(i & 1) * 2], vf[i >> 2][1][(i >> 1) & 1][(i & 1) * 2 + 1]);
          if (h == 0) PUMP1() else mbar_wait(bar_done + 30 * 8, par);
          if (fold) mbar_wait(bar_phi, 1);
#pragma unroll
          for (int i = 0; i < 4; i++) {
            const int hh = i >> 1, dp = i & 1;
            PMASKS(h, O_BIT(l));
            stsm_x4(pO + srowoff + ((hh * 64 + dp * 32 + lhi) ^ lsw), PBIT0(pack_bf16(o[hh][dp * 2][0], o[hh][dp * 2][1])), PBIT0(pack_bf16(o[hh][dp * 2][2], o[hh][dp * 2][3])),
                    PBIT1(pack_bf16(o[hh][dp * 2 + 1][0], o[hh][dp * 2 + 1][1])), PBIT1(pack_bf16(o[hh][dp * 2 + 1][2], o[hh][dp * 2 + 1][3])));
          }
          PUBLISH_O();
          PROF(11 + h * 12);
          if (h) break;
          if (fold) { PUMPS(FPUMP); FOLD(pK, 1); }
          REST_P1(ASKEW);
          if (fold) mbar_wait(bar_phi + 8, 1);
          DRAIN_A(S1, {});
        }
      } else {
        constexpr uint32_t par = 1;
        float st[64];
        DRAIN_B(S0);
        if (warp < 2) sts128(sbase + OFF_ONES + warp * 512 + lane * 16, 0x3F803F80u, 0x3F803F80u, 0x3F803F80u, 0x3F803F80u);
        const float c0 = rs0 * LOG2E, c1 = rs1 * LOG2E;
#pragma unroll 1
        for (int h = 0; h < 2; h++) {
          const uint32_t pO = sbase + (h ? 3 : 12) * SLOT, pP = sbase + (h ? 9 : 10) * SLOT;
          PROF(4 + h * 12);
          SITE(0);
          LANE_CONSTS();
          const uint32_t dsw = (uint32_t)(g ^ (2 * t)) << 4;
          const float* pk = st + 32;
          float4* kvg = reinterpret_cast<float4*>(g_kv[l >> 1] + (jj * 4 + h * 2 + wg) * KVH) + (warp & 3) * 32 + lane;
          const uint32_t dst = ((t & 2) ? pP : pO) + (r0 + g) * 128;
          float mq[4];
          {
            float e[16], f[16];
            float mn0 = rmin16(pk);
            asm volatile("" : "+f"(mn0)); SCHED_FENCE();
            float sa = exps16(e, pk, -c0, mn0 * c0), mx0 = rmax16(pk);
            asm volatile("" : "+f"(sa), "+f"(mx0)); PIN(e, 16); SITE(1);
            store16(e, sa, dst, dsw, 4);
            float sb = exps16(f, pk, c0, -mx0 * c0), mn1 = rmin16(pk + 2);
            asm volatile("" : "+f"(sb), "+f"(mn1)); PIN(f, 16); SITE(2);
            float kv0[20];
#pragma unroll
            for (int i = 0; i < 20; i++) kv0[i] = 0.f;
            if (h) KV_LOAD(kv0, 0);
            store16(f, sb, dst, dsw, 0);
            float sc = exps16(e, pk + 2, -c1, mn1 * c1), mx1 = rmax16(pk + 2);
            asm volatile("" : "+f"(sc), "+f"(mx1)); PIN(e, 16); SITE(3);
            store16(e, sc, dst + 1024, dsw, 4);
            float sd = exps16(f, pk + 2, c1, -mx1 * c1);
            asm volatile("" : "+f"(sd)); PIN(f, 16); SITE(4);
            store16(f, sd, dst + 1024, dsw, 0);
            if (h) KV_TILE(kv0, sbase + 8 * SLOT);
          }
          fence_proxy_async_smem();
          STG_ARRIVE();
          PROF(5 + h * 12);
          uint32_t fq[32];
          {
            const uint64_t dp = make_desc(wg ? pP : pO, 16, 1024);
            const uint64_t dv = (make_desc(pV + wg * 8192, OFF_ONES - OFF_S - SLOT - wg * 8192, 512) ^ (3ull << 62));
            constexpr uint64_t DVS = 64ull - (64ull << 16);
            mq[0] = rmin16(st);
            asm volatile("" : "+f"(mq[0])); SITE(5);
            STG_WAIT();
            PROF(8 + h * 12);
#define KV_MMA() \
              float kv[20]; \
              ACC_DEF(kv, 20); \
              wgmma_fence(); \
              _Pragma("unroll") for (int ks = 0; ks < 8; ks++) { if (ks == 0) wgmma_n40<0, 1>(kv, dp, dv); else wgmma_n40<1, 1>(kv, dp + ks * 128, dv + ks * DVS); } \
              wgmma_commit();
#define KV_OUT(...) { \
              SCHED_FENCE(); \
              mq[1] = rmax16(st); mq[2] = rmin16(st + 2); mq[3] = rmax16(st + 2); \
              asm volatile("" : "+f"(mq[1]), "+f"(mq[2]), "+f"(mq[3])); \
              PROF(9 + h * 12); \
              __VA_ARGS__; \
              PROF(10 + h * 12); \
              ACC_FENCE(kv, 20); \
              _Pragma("unroll") for (int i = 0; i < 5; i++) red_v4(reinterpret_cast<float*>(kvg + i * 128), kv[i * 4], kv[i * 4 + 1], kv[i * 4 + 2], kv[i * 4 + 3]); \
              asm volatile("bar.arrive %0, 288;" :: "r"(BAR_KV + h) : "memory"); \
              STG_ARRIVE(); \
              PROF(6 + h * 12); }
            if (h == 0) { KV_MMA(); KV_OUT(PUMP0()); } else {
              float o[96];
              wgmma_wait<0>();
              ACC_DEF(o, 96);
              KV_MMA();
              KV_OUT({ wgmma_fence(); O_MMA(o, sbase + 12 * SLOT, sbase + 10 * SLOT, sbase + 8 * SLOT); wgmma_wait<1>(); });
              wgmma_wait<0>();
              ACC_FENCE(o, 20); ACC_FENCE((o + 24), 20); ACC_FENCE((o + 48), 20); ACC_FENCE((o + 72), 20);
              O_OUT(o, sbase + 12 * SLOT, 0);
              PROF(26);
              LOAD_X();
            }
          }
          expp16(fq, st, -c0, mq[0] * c0);
          PINU(fq, 8); SITE(6);
          expp16(fq + 8, st, c0, -mq[1] * c0);
          PINU(fq + 8, 8); SITE(7);
          STG_WAIT();
#pragma unroll
          for (int i = 0; i < 4; i++) sts128(dst + (((((i & 2) ? 0 : 4) + (i & 1)) << 4) ^ dsw), fq[i * 4], fq[i * 4 + 1], fq[i * 4 + 2], fq[i * 4 + 3]);
          expp16(fq + 16, st + 2, -c1, mq[2] * c1);
          PINU(fq + 16, 8); SITE(8);
          expp16(fq + 24, st + 2, c1, -mq[3] * c1);
#pragma unroll
          for (int i = 4; i < 8; i++) sts128(dst + 1024 + (((((i & 2) ? 0 : 4) + (i & 1)) << 4) ^ dsw), fq[i * 4], fq[i * 4 + 1], fq[i * 4 + 2], fq[i * 4 + 3]);
          PROF(7 + h * 12);
          if (h) break;
          REST_P1(1);
          DRAIN_B(S1);
        }
        {
          LANE_CONSTS();
          bar_wg(wg);
          WSTEP();
          wgmma_wait<0>();
          REL(bar_done + 32 * 8);
          float o[96];
          KV_LOAD(o, 1);
          PROF(32);
          KV_TILE(o, pV);
          fence_proxy_async_smem();
          STG_ARRIVE();
          ACC_DEF(o, 96);
          STG_WAIT();
          PROF(33);
          wgmma_fence();
          O_MMA(o, sbase + 3 * SLOT, sbase + 9 * SLOT, pV);
          wgmma_wait<0>();
          ACC_FENCE(o, 20); ACC_FENCE((o + 24), 20); ACC_FENCE((o + 48), 20); ACC_FENCE((o + 72), 20);
          O_OUT(o, sbase + 3 * SLOT, 1);
          PROF(34);
        }
      }
      __syncwarp();
      if (elect_one()) mbar_arrive_local(bar_epi);
      bar_wg(wg);
#pragma unroll 1
      while (ub < bar_full + 384) {
        WSTEP();
        if (ub == bar_full + 8 * 41) PROF(35);
        if (ub == bar_full + 8 * 42) PROF(36);
      }
      wgmma_wait<0>();
      ACC_FENCE(S1, 64);
      REL(bar_done + 47 * 8);
      PROF(37);
      {
      LANE_CONSTS();
#pragma unroll
      for (int j = 0; j < 8; j++) {
        PMASKS(l < NLAYERS - 1 && j < 4, X_BIT(l));
        stsm_x4(pK + (j >> 2) * SLOT + srowoff + ((((uint32_t)(j & 3) << 5) + lhi) ^ lsw),
                PBIT0(pack_bf16(S1[j * 8 + 0], S1[j * 8 + 1])), PBIT0(pack_bf16(S1[j * 8 + 2], S1[j * 8 + 3])),
                PBIT1(pack_bf16(S1[j * 8 + 4], S1[j * 8 + 5])), PBIT1(pack_bf16(S1[j * 8 + 6], S1[j * 8 + 7])));
        if (j == 3) { fence_proxy_async_smem(); bar_arrive<BAR_O + 2, 288>(); }
      }
      }
      fence_proxy_async_smem();
      bar_arrive<BAR_O + 3, 288>();
      PROF(38);
    }
    const int tid = threadIdx.x;
    if (tid == 0) {
      unsigned old = atomicAdd(&g_flags.done.v, 1);
      if (old == ep1 * NMAIN - 1) {
        asm volatile("st.relaxed.gpu.global.u32 [%0], %1;" :: "l"(&g_flags.epoch.v), "r"(ep1) : "memory");
      }
    }
    __syncwarp();
    cluster_sync();
  }
}

typedef CUresult (*PFN_encode)(CUtensorMap*, CUtensorMapDataType, cuuint32_t, void*, const cuuint64_t*, const cuuint64_t*,
                               const cuuint32_t*, const cuuint32_t*, CUtensorMapInterleave, CUtensorMapSwizzle,
                               CUtensorMapL2promotion, CUtensorMapFloatOOBfill);

CUtensorMap make_map(PFN_encode enc, const void* ptr, uint64_t inner, uint64_t outer, uint32_t box_inner, uint32_t box_outer,
                     CUtensorMapSwizzle swz = CU_TENSOR_MAP_SWIZZLE_128B) {
  CUtensorMap m;
  cuuint64_t dims[2] = {inner, outer};
  cuuint64_t strides[1] = {inner * 2};
  cuuint32_t box[2] = {box_inner, box_outer};
  cuuint32_t es[2] = {1, 1};
  enc(&m, CU_TENSOR_MAP_DATA_TYPE_BFLOAT16, 2, const_cast<void*>(ptr), dims, strides, box, es, CU_TENSOR_MAP_INTERLEAVE_NONE,
      swz, CU_TENSOR_MAP_L2_PROMOTION_L2_256B, CU_TENSOR_MAP_FLOAT_OOB_FILL_NONE);
  return m;
}

}

extern "C" void kernel_launch(void* const* d_in, const int* in_sizes, int n_in, void* d_out, int out_size) {
  (void)in_sizes; (void)n_in; (void)out_size;
  static PFN_encode enc = nullptr;
  if (!enc) {
    void* fn = nullptr;
    cudaDriverEntryPointQueryResult qr;
    cudaGetDriverEntryPoint("cuTensorMapEncodeTiled", &fn, cudaEnableDefault, &qr);
    enc = (PFN_encode)fn;
    cudaFuncSetAttribute(mega_kernel, cudaFuncAttributeMaxDynamicSharedMemorySize, SMEM_BYTES);
  }
  Params prm;
  prm.x0 = (const __nv_bfloat16*)d_in[0];
  prm.wA_qkv = (const __nv_bfloat16*)d_in[1];
  prm.wA_o = (const __nv_bfloat16*)d_in[2];
  prm.wB_qkv = (const __nv_bfloat16*)d_in[4];
  prm.wB_phi = (const __nv_bfloat16*)d_in[5];
  prm.wB_o = (const __nv_bfloat16*)d_in[6];
  prm.out = (__nv_bfloat16*)d_out;
  void *obuf = nullptr, *xbuf = nullptr, *wf = nullptr;
  cudaGetSymbolAddress(&obuf, g_obuf);
  cudaGetSymbolAddress(&xbuf, g_xbuf);
  cudaGetSymbolAddress(&wf, g_wfold);
  CUtensorMap tm_x0 = make_map(enc, d_in[0], D_MODEL, S_LEN, 64, 128);
  CUtensorMap tm_xo = make_map(enc, d_out, D_MODEL, S_LEN, 64, 128);
  CUtensorMap tm_xb = make_map(enc, xbuf, D_MODEL, S_LEN, 64, 128);
  CUtensorMap tm_o = make_map(enc, obuf, D_MODEL, S_LEN, 64, 128);
  CUtensorMap tm_wf = make_map(enc, wf, 2048, D_MODEL, 64, 32);
  CUtensorMap tm_wqA = make_map(enc, d_in[1], 3 * D_MODEL, D_MODEL, 64, 32);
  CUtensorMap tm_wqB = make_map(enc, prm.wB_qkv, 3 * D_MODEL, D_MODEL, 64, 32);
  CUtensorMap tm_woA = make_map(enc, prm.wA_o, D_MODEL, D_MODEL, 64, 64);
  CUtensorMap tm_woB = make_map(enc, prm.wB_o, D_MODEL, D_MODEL, 64, 64);
  CUtensorMap tm_phi = make_map(enc, prm.wB_phi, 32, 1024, 32, 128, CU_TENSOR_MAP_SWIZZLE_64B);
  mega_kernel<<<NMAIN + NAUX, 384, SMEM_BYTES>>>(tm_x0, tm_xo, tm_xb, tm_o, tm_wf, tm_wqA, tm_wqB, tm_woA, tm_woB, tm_phi, prm);
}
```

```cpp
#include <cuda_runtime.h>
#include <cuda.h>
#include <cuda_bf16.h>
#include <stdint.h>

#define NLAYERS 4

#define STAG1 300
#define HPUMP1 2
#define HPUMP2 2
#define ASKEW 2
#define FPUMP 2
#define PFGAP 100
#define KVPUMP 3
#define KVPUMP2 2
#define KVWO 4
#define POLLW 4
#define POLL0 0
#define POLLGAP 120
#define BMASK 0x09E
#define ASITE 1
namespace {

constexpr int S_LEN = 2048, D_MODEL = 1024;
constexpr int NAUX = 4, NMAIN = 128;
constexpr int SLOT = 16384;
constexpr int QST = 24576;
constexpr int OFF_RA = 6 * SLOT, OFF_S = 10 * SLOT;
constexpr int OFF_HALO = 13 * SLOT, OFF_LNB = OFF_HALO  , OFF_ONES = OFF_HALO + 3072;
constexpr int OFF_ST = OFF_HALO + 7168  , OFF_PHI = OFF_HALO + 8192;
constexpr int OFF_BAR = 14 * SLOT;
constexpr int OFF_LNA = OFF_BAR + 1024;
constexpr int SMEM_BYTES = OFF_LNA + 2048;
constexpr unsigned long long WO_ASLOT = 0x98C76BA398C7698Cull;
constexpr unsigned long long WO_BSLOT = 0x5432105421054210ull;
__device__ __forceinline__ int kslice(int j, int i) { return i < 2 ? 2 * j + i : (i < 9 ? 2 * ((j + i - 1) & 7) : 2 * ((j + i) & 7) + 1); }
__device__ __forceinline__ int wslice(int j, int s) { return 2 * ((j + s) & 7) + (s >> 3); }
constexpr int KVH = 5 * 128 * 4;

struct __align__(128) Flag { unsigned v; unsigned pad[31]; };
struct Flags {
  Flag xready[4][16];
  Flag oready[4][16];
  Flag kvready[4][8][16];
  Flag wfready[8];
  Flag done;
  Flag epoch;
};

__device__ Flags g_flags;
__device__ __nv_bfloat16 g_obuf[2 * S_LEN * D_MODEL];
#define O_BIT(l) ((epoch * NLAYERS + (l) + 1) & 1u)
#define X_BIT(l) ((epoch * (NLAYERS - 1) + (l) + 1) & 1u)
__device__ __nv_bfloat16 g_wfold[D_MODEL * 2048];
__device__ uint4 g_halo[16 * 8 * 512];
__device__ float g_kv[2][32 * KVH];
__device__ __align__(128) uint2 g_colsum[2][1536][2];
__device__ __align__(128) uint2 g_stats[S_LEN * 8];
#define STAT_TAG(l) ((ep1 * NLAYERS + (l) + 1) & 3u)

#define RETRY_COUNT()
#define PROFL 1
#define PROFW 0
#define KVFLAG 1
#define PROFT(i) do {} while (0)
#define PROF(i) do {} while (0)

__device__ __forceinline__ uint32_t smem_u32(const void* p) { return (uint32_t)__cvta_generic_to_shared(p); }
__device__ __forceinline__ bool elect_one() {
  uint32_t p;
  asm volatile("{\n.reg .pred p;\nelect.sync _|p, 0xffffffff;\nselp.u32 %0, 1, 0, p;\n}\n" : "=r"(p));
  return p != 0;
}
__device__ __forceinline__ void mbar_init(uint32_t bar, uint32_t cnt) {
  asm volatile("mbarrier.init.shared::cta.b64 [%0], %1;" :: "r"(bar), "r"(cnt));
}
__device__ __forceinline__ void mbar_expect_tx(uint32_t bar, uint32_t bytes) {
  asm volatile("mbarrier.arrive.expect_tx.shared::cta.b64 _, [%0], %1;" :: "r"(bar), "r"(bytes) : "memory");
}
#define mbar_wait(bar, parity) \
  asm volatile("{\n.reg .pred p, q;\nW_%=:\nmbarrier.try_wait.parity.shared::cta.b64 p, [%1], %2;\nadd.s32 %0, %0, -1;\n" \
               "setp.gt.and.s32 q, %0, 0, !p;\n@q bra W_%=;\n}\n" : "+r"(budget) : "r"((uint32_t)(bar)), "r"((uint32_t)(parity)) : "memory")
#define mbar_wait_sl(bar, parity) \
  asm volatile("{\n.reg .pred p, q;\nW_%=:\nmbarrier.try_wait.parity.shared::cta.b64 p, [%1], %2, 20000;\nadd.s32 %0, %0, -64;\n" \
               "setp.gt.and.s32 q, %0, 0, !p;\n@q bra W_%=;\n}\n" : "+r"(budget) : "r"((uint32_t)(bar)), "r"((uint32_t)(parity)) : "memory")
__device__ __forceinline__ void mbar_arrive_local(uint32_t bar) {
  asm volatile("mbarrier.arrive.shared::cta.b64 _, [%0];" :: "r"(bar) : "memory");
}
__device__ __forceinline__ void tma_load_2d(uint32_t dst, const CUtensorMap* tm, uint32_t bar, int c0, int c1) {
  asm volatile("cp.async.bulk.tensor.2d.shared::cluster.global.mbarrier::complete_tx::bytes [%0], [%1, {%3, %4}], [%2];"
               :: "r"(dst), "l"(tm), "r"(bar), "r"(c0), "r"(c1) : "memory");
}
__device__ __forceinline__ void tma_load_2d_mc(uint32_t dst, const CUtensorMap* tm, uint32_t bar, int c0, int c1) {
  asm volatile("cp.async.bulk.tensor.2d.shared::cluster.global.mbarrier::complete_tx::bytes.multicast::cluster [%0], [%1, {%3, %4}], [%2], %5;"
               :: "r"(dst), "l"(tm), "r"(bar), "r"(c0), "r"(c1), "h"((uint16_t)3) : "memory");
}
__device__ __forceinline__ void tma_store_2d(const CUtensorMap* tm, uint32_t src, int c0, int c1) {
  asm volatile("cp.async.bulk.tensor.2d.global.shared::cta.bulk_group [%0, {%2, %3}], [%1];"
               :: "l"(tm), "r"(src), "r"(c0), "r"(c1) : "memory");
}
__device__ __forceinline__ void bulk_commit_wait() {
  asm volatile("cp.async.bulk.commit_group;\ncp.async.bulk.wait_group 0;" ::: "memory");
}
__device__ __forceinline__ void prefetch_tmap(const CUtensorMap* tm) {
  asm volatile("prefetch.tensormap [%0];" :: "l"(tm) : "memory");
}
__device__ __forceinline__ void fence_proxy_async_global() { asm volatile("fence.proxy.async.global;" ::: "memory"); }
__device__ __forceinline__ void fence_proxy_async_smem() { asm volatile("fence.proxy.async.shared::cta;" ::: "memory"); }
__device__ __forceinline__ unsigned ld_relaxed(const unsigned* p) {
  unsigned v;
  asm volatile("ld.relaxed.gpu.global.u32 %0, [%1];" : "=r"(v) : "l"(p) : "memory");
  return v;
}
__device__ __forceinline__ void fence_acquire() { asm volatile("fence.acquire.gpu;" ::: "memory"); }
__device__ __forceinline__ void wait_flag(const unsigned* p, unsigned target) {
  int it = 0;
  while ((int)(ld_relaxed(p) - target) < 0 && ++it < (1 << 20)) {}
  fence_acquire();
}
__device__ __forceinline__ void signal_release(unsigned* p) {
  asm volatile("red.release.gpu.global.add.u32 [%0], 1;" :: "l"(p) : "memory");
}
template <int ID, int N> __device__ __forceinline__ void bar_arrive() { asm volatile("bar.arrive %0, %1;" :: "n"(ID), "n"(N) : "memory"); }
template <int ID, int N> __device__ __forceinline__ void bar_sync() { asm volatile("bar.sync %0, %1;" :: "n"(ID), "n"(N) : "memory"); }
__device__ __forceinline__ void bar_wg(int wg) { asm volatile("bar.sync %0, 128;" :: "r"(2 + wg) : "memory"); }
__device__ __forceinline__ void cluster_sync() {
  asm volatile("barrier.cluster.arrive.relaxed.aligned;\nbarrier.cluster.wait.aligned;" ::: "memory");
}
__device__ __forceinline__ void cluster_wait() { asm volatile("barrier.cluster.wait.acquire.aligned;" ::: "memory"); }
enum { BAR_KV = 4  , BAR_O = 7  , BAR_WF = 12  , BAR_SKEW = 13 };

__device__ __forceinline__ void wgmma_fence() { asm volatile("wgmma.fence.sync.aligned;" ::: "memory"); }
__device__ __forceinline__ void wgmma_commit() { asm volatile("wgmma.commit_group.sync.aligned;" ::: "memory"); }
template <int N> __device__ __forceinline__ void wgmma_wait() { asm volatile("wgmma.wait_group.sync.aligned %0;" :: "n"(N) : "memory"); }

template <int scale_d, int tnsp_b = 1> __device__ __forceinline__ void wgmma_n192(float* d, uint64_t descA, uint64_t descB) {
  asm volatile("{\n.reg .pred p;\nsetp.ne.b32 p, %98, 0;\n"
               "wgmma.mma_async.sync.aligned.m64n192k16.f32.bf16.bf16 {%0,%1,%2,%3,%4,%5,%6,%7,%8,%9,%10,%11,%12,%13,%14,%15,%16,%17,%18,%19,%20,%21,%22,%23,%24,%25,%26,%27,%28,%29,%30,%31,%32,%33,%34,%35,%36,%37,%38,%39,%40,%41,%42,%43,%44,%45,%46,%47,%48,%49,%50,%51,%52,%53,%54,%55,%56,%57,%58,%59,%60,%61,%62,%63,%64,%65,%66,%67,%68,%69,%70,%71,%72,%73,%74,%75,%76,%77,%78,%79,%80,%81,%82,%83,%84,%85,%86,%87,%88,%89,%90,%91,%92,%93,%94,%95}, %96, %97, p, 1, 1, 0, %99;\n}\n"
               : "+f"(d[0]), "+f"(d[1]), "+f"(d[2]), "+f"(d[3]), "+f"(d[4]), "+f"(d[5]), "+f"(d[6]), "+f"(d[7]), "+f"(d[8]), "+f"(d[9]), "+f"(d[10]), "+f"(d[11]), "+f"(d[12]), "+f"(d[13]), "+f"(d[14]), "+f"(d[15]), "+f"(d[16]), "+f"(d[17]), "+f"(d[18]), "+f"(d[19]), "+f"(d[20]), "+f"(d[21]), "+f"(d[22]), "+f"(d[23]), "+f"(d[24]), "+f"(d[25]), "+f"(d[26]), "+f"(d[27]), "+f"(d[28]), "+f"(d[29]), "+f"(d[30]), "+f"(d[31]), "+f"(d[32]), "+f"(d[33]), "+f"(d[34]), "+f"(d[35]), "+f"(d[36]), "+f"(d[37]), "+f"(d[38]), "+f"(d[39]), "+f"(d[40]), "+f"(d[41]), "+f"(d[42]), "+f"(d[43]), "+f"(d[44]), "+f"(d[45]), "+f"(d[46]), "+f"(d[47]), "+f"(d[48]), "+f"(d[49]), "+f"(d[50]), "+f"(d[51]), "+f"(d[52]), "+f"(d[53]), "+f"(d[54]), "+f"(d[55]), "+f"(d[56]), "+f"(d[57]), "+f"(d[58]), "+f"(d[59]), "+f"(d[60]), "+f"(d[61]), "+f"(d[62]), "+f"(d[63]), "+f"(d[64]), "+f"(d[65]), "+f"(d[66]), "+f"(d[67]), "+f"(d[68]), "+f"(d[69]), "+f"(d[70]), "+f"(d[71]), "+f"(d[72]), "+f"(d[73]), "+f"(d[74]), "+f"(d[75]), "+f"(d[76]), "+f"(d[77]), "+f"(d[78]), "+f"(d[79]), "+f"(d[80]), "+f"(d[81]), "+f"(d[82]), "+f"(d[83]), "+f"(d[84]), "+f"(d[85]), "+f"(d[86]), "+f"(d[87]), "+f"(d[88]), "+f"(d[89]), "+f"(d[90]), "+f"(d[91]), "+f"(d[92]), "+f"(d[93]), "+f"(d[94]), "+f"(d[95])
               : "l"(descA), "l"(descB), "n"(scale_d), "n"(tnsp_b));
}
template <int scale_d> __device__ __forceinline__ void wgmma4_n192(float* d, uint32_t da, uint32_t db) {
#define R_ "{%0,%1,%2,%3,%4,%5,%6,%7,%8,%9,%10,%11,%12,%13,%14,%15,%16,%17,%18,%19,%20,%21,%22,%23,%24,%25,%26,%27,%28,%29,%30,%31,%32,%33,%34,%35,%36,%37,%38,%39,%40,%41,%42,%43,%44,%45,%46,%47,%48,%49,%50,%51,%52,%53,%54,%55,%56,%57,%58,%59,%60,%61,%62,%63,%64,%65,%66,%67,%68,%69,%70,%71,%72,%73,%74,%75,%76,%77,%78,%79,%80,%81,%82,%83,%84,%85,%86,%87,%88,%89,%90,%91,%92,%93,%94,%95}"
  asm volatile("{\n.reg .pred p, q;\n.reg .b64 a, b;\nsetp.ne.b32 p, %98, 0;\nsetp.eq.b32 q, 0, 0;\nmov.b64 a, {%96, 0x40000040};\nmov.b64 b, {%97, 0x40000040};\n"
               "wgmma.mma_async.sync.aligned.m64n192k16.f32.bf16.bf16 " R_ ", a, b, p, 1, 1, 0, 1;\nadd.s64 a, a, 2;\nadd.s64 b, b, 128;\n"
               "wgmma.mma_async.sync.aligned.m64n192k16.f32.bf16.bf16 " R_ ", a, b, q, 1, 1, 0, 1;\nadd.s64 a, a, 2;\nadd.s64 b, b, 128;\n"
               "wgmma.mma_async.sync.aligned.m64n192k16.f32.bf16.bf16 " R_ ", a, b, q, 1, 1, 0, 1;\nadd.s64 a, a, 2;\nadd.s64 b, b, 128;\n"
               "wgmma.mma_async.sync.aligned.m64n192k16.f32.bf16.bf16 " R_ ", a, b, q, 1, 1, 0, 1;\n}\n"
               : "+f"(d[0]), "+f"(d[1]), "+f"(d[2]), "+f"(d[3]), "+f"(d[4]), "+f"(d[5]), "+f"(d[6]), "+f"(d[7]), "+f"(d[8]), "+f"(d[9]), "+f"(d[10]), "+f"(d[11]), "+f"(d[12]), "+f"(d[13]), "+f"(d[14]), "+f"(d[15]), "+f"(d[16]), "+f"(d[17]), "+f"(d[18]), "+f"(d[19]), "+f"(d[20]), "+f"(d[21]), "+f"(d[22]), "+f"(d[23]), "+f"(d[24]), "+f"(d[25]), "+f"(d[26]), "+f"(d[27]), "+f"(d[28]), "+f"(d[29]), "+f"(d[30]), "+f"(d[31]), "+f"(d[32]), "+f"(d[33]), "+f"(d[34]), "+f"(d[35]), "+f"(d[36]), "+f"(d[37]), "+f"(d[38]), "+f"(d[39]), "+f"(d[40]), "+f"(d[41]), "+f"(d[42]), "+f"(d[43]), "+f"(d[44]), "+f"(d[45]), "+f"(d[46]), "+f"(d[47]), "+f"(d[48]), "+f"(d[49]), "+f"(d[50]), "+f"(d[51]), "+f"(d[52]), "+f"(d[53]), "+f"(d[54]), "+f"(d[55]), "+f"(d[56]), "+f"(d[57]), "+f"(d[58]), "+f"(d[59]), "+f"(d[60]), "+f"(d[61]), "+f"(d[62]), "+f"(d[63]), "+f"(d[64]), "+f"(d[65]), "+f"(d[66]), "+f"(d[67]), "+f"(d[68]), "+f"(d[69]), "+f"(d[70]), "+f"(d[71]), "+f"(d[72]), "+f"(d[73]), "+f"(d[74]), "+f"(d[75]), "+f"(d[76]), "+f"(d[77]), "+f"(d[78]), "+f"(d[79]), "+f"(d[80]), "+f"(d[81]), "+f"(d[82]), "+f"(d[83]), "+f"(d[84]), "+f"(d[85]), "+f"(d[86]), "+f"(d[87]), "+f"(d[88]), "+f"(d[89]), "+f"(d[90]), "+f"(d[91]), "+f"(d[92]), "+f"(d[93]), "+f"(d[94]), "+f"(d[95])
               : "r"(da), "r"(db), "n"(scale_d));
#undef R_
}
template <int scale_d> __device__ __forceinline__ void wgmma4_n128(float* d, uint32_t da, uint32_t db) {
#define R_ "{%0,%1,%2,%3,%4,%5,%6,%7,%8,%9,%10,%11,%12,%13,%14,%15,%16,%17,%18,%19,%20,%21,%22,%23,%24,%25,%26,%27,%28,%29,%30,%31,%32,%33,%34,%35,%36,%37,%38,%39,%40,%41,%42,%43,%44,%45,%46,%47,%48,%49,%50,%51,%52,%53,%54,%55,%56,%57,%58,%59,%60,%61,%62,%63}"
  asm volatile("{\n.reg .pred p, q;\n.reg .b64 a, b;\nsetp.ne.b32 p, %66, 0;\nsetp.eq.b32 q, 0, 0;\nmov.b64 a, {%64, 0x40000040};\nmov.b64 b, {%65, 0x40000040};\n"
               "wgmma.mma_async.sync.aligned.m64n128k16.f32.bf16.bf16 " R_ ", a, b, p, 1, 1, 0, 1;\nadd.s64 a, a, 2;\nadd.s64 b, b, 128;\n"
               "wgmma.mma_async.sync.aligned.m64n128k16.f32.bf16.bf16 " R_ ", a, b, q, 1, 1, 0, 1;\nadd.s64 a, a, 2;\nadd.s64 b, b, 128;\n"
               "wgmma.mma_async.sync.aligned.m64n128k16.f32.bf16.bf16 " R_ ", a, b, q, 1, 1, 0, 1;\nadd.s64 a, a, 2;\nadd.s64 b, b, 128;\n"
               "wgmma.mma_async.sync.aligned.m64n128k16.f32.bf16.bf16 " R_ ", a, b, q, 1, 1, 0, 1;\n}\n"
               : "+f"(d[0]), "+f"(d[1]), "+f"(d[2]), "+f"(d[3]), "+f"(d[4]), "+f"(d[5]), "+f"(d[6]), "+f"(d[7]), "+f"(d[8]), "+f"(d[9]), "+f"(d[10]), "+f"(d[11]), "+f"(d[12]), "+f"(d[13]), "+f"(d[14]), "+f"(d[15]), "+f"(d[16]), "+f"(d[17]), "+f"(d[18]), "+f"(d[19]), "+f"(d[20]), "+f"(d[21]), "+f"(d[22]), "+f"(d[23]), "+f"(d[24]), "+f"(d[25]), "+f"(d[26]), "+f"(d[27]), "+f"(d[28]), "+f"(d[29]), "+f"(d[30]), "+f"(d[31]), "+f"(d[32]), "+f"(d[33]), "+f"(d[34]), "+f"(d[35]), "+f"(d[36]), "+f"(d[37]), "+f"(d[38]), "+f"(d[39]), "+f"(d[40]), "+f"(d[41]), "+f"(d[42]), "+f"(d[43]), "+f"(d[44]), "+f"(d[45]), "+f"(d[46]), "+f"(d[47]), "+f"(d[48]), "+f"(d[49]), "+f"(d[50]), "+f"(d[51]), "+f"(d[52]), "+f"(d[53]), "+f"(d[54]), "+f"(d[55]), "+f"(d[56]), "+f"(d[57]), "+f"(d[58]), "+f"(d[59]), "+f"(d[60]), "+f"(d[61]), "+f"(d[62]), "+f"(d[63])
               : "r"(da), "r"(db), "n"(scale_d));
#undef R_
}
template <int scale_d> __device__ __forceinline__ void wgmma_n32(float* d, uint64_t descA, uint64_t descB) {
  asm volatile("{\n.reg .pred p;\nsetp.ne.b32 p, %18, 0;\n"
               "wgmma.mma_async.sync.aligned.m64n32k16.f32.bf16.bf16 {%0,%1,%2,%3,%4,%5,%6,%7,%8,%9,%10,%11,%12,%13,%14,%15}, %16, %17, p, 1, 1, 0, 1;\n}\n"
               : "+f"(d[0]), "+f"(d[1]), "+f"(d[2]), "+f"(d[3]), "+f"(d[4]), "+f"(d[5]), "+f"(d[6]), "+f"(d[7]), "+f"(d[8]), "+f"(d[9]), "+f"(d[10]), "+f"(d[11]), "+f"(d[12]), "+f"(d[13]), "+f"(d[14]), "+f"(d[15])
               : "l"(descA), "l"(descB), "n"(scale_d));
}
template <int scale_d, int tnsp_a> __device__ __forceinline__ void wgmma_n40(float* d, uint64_t descA, uint64_t descB) {
  asm volatile("{\n.reg .pred p;\nsetp.ne.b32 p, %22, 0;\n"
               "wgmma.mma_async.sync.aligned.m64n40k16.f32.bf16.bf16 {%0,%1,%2,%3,%4,%5,%6,%7,%8,%9,%10,%11,%12,%13,%14,%15,%16,%17,%18,%19}, %20, %21, p, 1, 1, %23, 1;\n}\n"
               : "+f"(d[0]), "+f"(d[1]), "+f"(d[2]), "+f"(d[3]), "+f"(d[4]), "+f"(d[5]), "+f"(d[6]), "+f"(d[7]), "+f"(d[8]), "+f"(d[9]), "+f"(d[10]), "+f"(d[11]), "+f"(d[12]), "+f"(d[13]), "+f"(d[14]), "+f"(d[15]), "+f"(d[16]), "+f"(d[17]), "+f"(d[18]), "+f"(d[19])
               : "l"(descA), "l"(descB), "n"(scale_d), "n"(tnsp_a));
}
__device__ __forceinline__ uint64_t make_desc(uint32_t addr, uint32_t lbo_bytes, uint32_t sbo_bytes) {
  return (uint64_t)((addr & 0x3FFFF) >> 4) | ((uint64_t)(lbo_bytes >> 4) << 16) | ((uint64_t)(sbo_bytes >> 4) << 32) | (1ull << 62);
}

__device__ __forceinline__ void ldsm_x4(uint32_t addr, uint32_t& r0, uint32_t& r1, uint32_t& r2, uint32_t& r3) {
  asm volatile("ldmatrix.sync.aligned.m8n8.x4.shared.b16 {%0,%1,%2,%3}, [%4];" : "=r"(r0), "=r"(r1), "=r"(r2), "=r"(r3) : "r"(addr) : "memory");
}
__device__ __forceinline__ void ldsm_x4_t(uint32_t addr, uint32_t& r0, uint32_t& r1, uint32_t& r2, uint32_t& r3) {
  asm volatile("ldmatrix.sync.aligned.m8n8.x4.trans.shared.b16 {%0,%1,%2,%3}, [%4];" : "=r"(r0), "=r"(r1), "=r"(r2), "=r"(r3) : "r"(addr) : "memory");
}
__device__ __forceinline__ void stsm_x4(uint32_t addr, uint32_t r0, uint32_t r1, uint32_t r2, uint32_t r3) {
  asm volatile("stmatrix.sync.aligned.m8n8.x4.shared.b16 [%0], {%1,%2,%3,%4};" :: "r"(addr), "r"(r0), "r"(r1), "r"(r2), "r"(r3) : "memory");
}
__device__ __forceinline__ void sts128(uint32_t addr, uint32_t a, uint32_t b, uint32_t c, uint32_t d) {
  asm volatile("st.shared.v4.u32 [%0], {%1,%2,%3,%4};" :: "r"(addr), "r"(a), "r"(b), "r"(c), "r"(d) : "memory");
}
__device__ __forceinline__ float lds32f(uint32_t addr) {
  float v;
  asm volatile("ld.shared.f32 %0, [%1];" : "=f"(v) : "r"(addr) : "memory");
  return v;
}
__device__ __forceinline__ void sts32f(uint32_t addr, float a) {
  asm volatile("st.shared.f32 [%0], %1;" :: "r"(addr), "f"(a) : "memory");
}
__device__ __forceinline__ void mma_bf16(float (&c)[4], uint32_t a0, uint32_t a1, uint32_t a2, uint32_t a3, uint32_t b0, uint32_t b1) {
  asm volatile("mma.sync.aligned.m16n8k16.row.col.f32.bf16.bf16.f32 {%0,%1,%2,%3}, {%4,%5,%6,%7}, {%8,%9}, {%0,%1,%2,%3};"
               : "+f"(c[0]), "+f"(c[1]), "+f"(c[2]), "+f"(c[3]) : "r"(a0), "r"(a1), "r"(a2), "r"(a3), "r"(b0), "r"(b1));
}
__device__ __forceinline__ uint32_t pack_bf16(float lo, float hi) {
  uint32_t r;
  asm("cvt.rn.bf16x2.f32 %0, %1, %2;" : "=r"(r) : "f"(hi), "f"(lo));
  return r;
}
__device__ __forceinline__ float bf_lo(uint32_t v) { return __uint_as_float(v << 16); }
__device__ __forceinline__ float bf_hi(uint32_t v) { return __uint_as_float(v & 0xFFFF0000u); }
__device__ __forceinline__ void split3(float x, uint32_t& h, uint32_t& m, uint32_t& l) {
  h = pack_bf16(x, 0.f); x -= bf_lo(h);
  m = pack_bf16(x, 0.f); x -= bf_lo(m);
  l = pack_bf16(x, 0.f);
}
__device__ __forceinline__ float ex2(float x) { float r; asm("ex2.approx.ftz.f32 %0, %1;" : "=f"(r) : "f"(x)); return r; }
__device__ __forceinline__ float rcp_fast(float x) { float r; asm("rcp.approx.ftz.f32 %0, %1;" : "=f"(r) : "f"(x)); return r; }
__device__ __forceinline__ void red_v4(float* p, float a, float b, float c, float d) {
  asm volatile("red.global.add.v4.f32 [%0], {%1, %2, %3, %4};" :: "l"(p), "f"(a), "f"(b), "f"(c), "f"(d) : "memory");
}
__device__ __forceinline__ uint4 ld_ll(const uint4* p) {
  uint4 v;
  asm volatile("{\n.reg .b64 a, b;\nld.relaxed.gpu.global.v2.b64 {a, b}, [%4];\nmov.b64 {%0, %1}, a;\nmov.b64 {%2, %3}, b;\n}\n"
               : "=r"(v.x), "=r"(v.y), "=r"(v.z), "=r"(v.w) : "l"(p) : "memory");
  return v;
}
__device__ __forceinline__ void st_b64(uint2* p, uint32_t a, uint32_t b) {
  asm volatile("{\n.reg .b64 v;\nmov.b64 v, {%1, %2};\nst.relaxed.gpu.global.b64 [%0], v;\n}\n" :: "l"(p), "r"(a), "r"(b) : "memory");
}
__device__ __forceinline__ void st_b128(uint4* p, uint32_t a, uint32_t b, uint32_t c, uint32_t d) {
  asm volatile("{\n.reg .b128 v;\nmov.b128 v, {%1, %2, %3, %4};\nst.relaxed.gpu.global.b128 [%0], v;\n}\n" :: "l"(p), "r"(a), "r"(b), "r"(c), "r"(d) : "memory");
}
__device__ __forceinline__ uint4 ld_b128(const uint4* p) {
  uint4 v;
  asm volatile("{\n.reg .b128 v;\nld.relaxed.gpu.global.b128 v, [%4];\nmov.b128 {%0, %1, %2, %3}, v;\n}\n" : "=r"(v.x), "=r"(v.y), "=r"(v.z), "=r"(v.w) : "l"(p) : "memory");
  return v;
}

constexpr float LOG2E = 1.4426950408889634f;

struct Params {
  const __nv_bfloat16* x0;
  const __nv_bfloat16* wA_qkv;
  const __nv_bfloat16* wA_o;
  const __nv_bfloat16* wB_qkv;
  const __nv_bfloat16* wB_phi;
  const __nv_bfloat16* wB_o;
  __nv_bfloat16* out;
};

#define ACC_DEF(d, n) _Pragma("unroll") for (int i_ = 0; i_ < (n); i_++) asm volatile("" : "=f"(d[i_]))
#define ACC_FENCE(d, n) _Pragma("unroll") for (int i_ = 0; i_ < (n); i_++) asm volatile("" : "+f"(d[i_]) :: "memory")
#define PIN(a, n) _Pragma("unroll") for (int i_ = 0; i_ < (n); i_++) asm volatile("" : "+f"((a)[i_]))
#define PINU(a, n) _Pragma("unroll") for (int i_ = 0; i_ < (n); i_++) asm volatile("" : "+r"((a)[i_]))

#define STAGE64(acc, off, p0, KIND, SEND) { \
    uint32_t w_[4][4]; \
    _Pragma("unroll") for (int j_ = 0; j_ < 4; j_++) { \
      const int o_ = (off) + j_ * 8; \
      w_[j_][0] = pack_bf16(rs0 * acc[o_ + 0], rs0 * acc[o_ + 1]); \
      w_[j_][1] = pack_bf16(rs1 * acc[o_ + 2], rs1 * acc[o_ + 3]); \
      w_[j_][2] = pack_bf16(rs0 * acc[o_ + 4], rs0 * acc[o_ + 5]); \
      w_[j_][3] = pack_bf16(rs1 * acc[o_ + 6], rs1 * acc[o_ + 7]); \
    } \
    if ((SEND) && hsend) { \
      _Pragma("unroll") for (int j_ = 0; j_ < 4; j_++) { \
        w_[j_][0] = (w_[j_][0] & ~1u) | hbit; \
        st_b128(hbase + lane + ((KIND) * 4 + j_) * 32, w_[j_][0], w_[j_][1], w_[j_][2], w_[j_][3]); \
      } \
    } \
    _Pragma("unroll") for (int j_ = 0; j_ < 4; j_++) \
      stsm_x4((KIND) ? (p0) + (j_ >> 1) * 8192 + (srowoff >> 1) + ((((uint32_t)(j_ & 1) << 5) + lhi) ^ lsw2) \
                     : (p0) + srowoff + ((((uint32_t)j_ << 5) + lhi) ^ lsw), \
              w_[j_][0], w_[j_][1], w_[j_][2], w_[j_][3]); \
  }
#define RW(j) (((j) >> 1) * 4 + ((j) & 1))
__device__ __forceinline__ float rmax16(const float* p) {
  float m[4];
#pragma unroll
  for (int j = 0; j < 4; j++) m[j] = fmaxf(fmaxf(p[RW(j)], p[RW(j + 4)]), fmaxf(p[RW(j + 8)], p[RW(j + 12)]));
  const float r = fmaxf(fmaxf(m[0], m[1]), fmaxf(m[2], m[3]));
  return fmaxf(r, __shfl_xor_sync(0xffffffffu, r, 1));
}
__device__ __forceinline__ float rmin16(const float* p) {
  float m[4];
#pragma unroll
  for (int j = 0; j < 4; j++) m[j] = fminf(fminf(p[RW(j)], p[RW(j + 4)]), fminf(p[RW(j + 8)], p[RW(j + 12)]));
  const float r = fminf(fminf(m[0], m[1]), fminf(m[2], m[3]));
  return fminf(r, __shfl_xor_sync(0xffffffffu, r, 1));
}
__device__ __forceinline__ float exps16(float* o, const float* p, float c, float b) {
  float s[4];
#pragma unroll
  for (int j = 0; j < 16; j++) { o[j] = ex2(fmaf(p[RW(j)], c, b)); if (j < 4) s[j] = o[j]; else s[j & 3] += o[j]; }
  return (s[0] + s[1]) + (s[2] + s[3]);
}
__device__ __forceinline__ void store16(const float* e, float sum, uint32_t dst, uint32_t dsw, int c0) {
  const float inv = rcp_fast(sum + __shfl_xor_sync(0xffffffffu, sum, 1));
#pragma unroll
  for (int j = 0; j < 2; j++)
    sts128(dst + (((c0 + j) << 4) ^ dsw), pack_bf16(e[j * 8] * inv, e[j * 8 + 1] * inv), pack_bf16(e[j * 8 + 2] * inv, e[j * 8 + 3] * inv),
           pack_bf16(e[j * 8 + 4] * inv, e[j * 8 + 5] * inv), pack_bf16(e[j * 8 + 6] * inv, e[j * 8 + 7] * inv));
}
__device__ __forceinline__ void expp16(uint32_t* o, const float* p, float c, float b) {
#pragma unroll
  for (int j = 0; j < 8; j++) o[j] = pack_bf16(ex2(fmaf(p[4 * j], c, b)), ex2(fmaf(p[4 * j + 1], c, b)));
}
#define SCHED_FENCE() asm volatile("pmevent 0;" ::: "memory")

__global__ void __cluster_dims__(2, 1, 1) __launch_bounds__(384, 1)
mega_kernel(const __grid_constant__ CUtensorMap tm_x0, const __grid_constant__ CUtensorMap tm_xo, const __grid_constant__ CUtensorMap tm_os,
            const __grid_constant__ CUtensorMap tm_o, const __grid_constant__ CUtensorMap tm_wf,
            const __grid_constant__ CUtensorMap tm_wqA, const __grid_constant__ CUtensorMap tm_wqB,
            const __grid_constant__ CUtensorMap tm_woA, const __grid_constant__ CUtensorMap tm_woB,
            const __grid_constant__ CUtensorMap tm_phi, const Params prm) {
  extern __shared__ __align__(1024) uint8_t smem_raw[];
  const uint32_t sbase = smem_u32(smem_raw);
  const uint32_t bar_full = sbase + OFF_BAR;
  const uint32_t bar_done = bar_full + 384;
  const uint32_t bar_stat = bar_full + 768, bar_stat2 = bar_full + 776, bar_epi = bar_full + 784, bar_phi = bar_full + 936  ;
  const uint32_t bar_xr = bar_full + 800, bar_lx = bar_full + 808, bar_kvf = bar_full + 816  , bar_stg = bar_full + 832;
  const uint32_t bar_chk = bar_full + 848;

  const int warp = __shfl_sync(0xffffffffu, threadIdx.x >> 5, 0), lane = threadIdx.x & 31;
  uint32_t rank;
  asm volatile("mov.u32 %0, %%cluster_ctarank;" : "=r"(rank));
  const int cta = (int)blockIdx.x - NAUX;
  const int cl = cta >> 1;
  const int jj = cl & 7, cc = cl >> 3;
  const int mm = cc * 2 + (int)rank;

#define LOAD_EPOCH() const unsigned epoch = ld_relaxed(&g_flags.epoch.v), ep1 = epoch + 1; (void)epoch
  int budget = 1 << 22;

  if (cta >= 0) {
    {
      const int tx = threadIdx.x;
      const __nv_bfloat16* pf = (tx < 128) ? prm.x0 + (size_t)(mm * 128 + tx) * D_MODEL + jj * 128
                                           : prm.wA_qkv + (size_t)(jj * 128 + (tx & 63)) * 3072 + ((tx - 128) >> 6) * 1024 + jj * 128 + rank * 64;
      if (tx < 320) asm volatile("prefetch.global.L2 [%0];" :: "l"(pf));
      else if (tx == 320) prefetch_tmap(&tm_x0);
      else if (tx == 352) prefetch_tmap(&tm_wqA);
      else if (tx == 383) asm volatile("prefetch.global.L2 [%0];" :: "l"(&g_flags.epoch.v));
    }
    if (elect_one()) {
#pragma unroll
      for (int i = 0; i < 4; i++) {
        const int u = warp * 4 + i;
        mbar_init(bar_full + u * 8, ((u >= 4 && u < 11) || u > 40) ? 2 : 1); mbar_init(bar_done + u * 8, 16);
      }
      mbar_init(bar_stat + warp * 16, 0x111111181182ull >> (4 * warp) & 15);
      mbar_init(bar_stat + warp * 16 + 8, 0x111111121811ull >> (4 * warp) & 15);
      asm volatile("fence.mbarrier_init.release.cluster;" ::: "memory");
    }
    __syncthreads();
    asm volatile("barrier.cluster.arrive.relaxed.aligned;" ::: "memory");
  }

  if (cta < 0) {
    LOAD_EPOCH();
    const uint32_t buf = sbase + warp * SLOT, bar = sbase + OFF_BAR + warp * 16;
    const uint32_t lsw = (lane & 7) << 4, lhi = (lane >> 4) << 4, lrow = (lane & 15) * 128;
    const bool el = elect_one();
    if (el) {
      mbar_init(bar, 1); mbar_init(bar + 8, 1);
      asm volatile("fence.mbarrier_init.release.cluster;" ::: "memory");
    }
#pragma unroll 1
    for (int rd = 0; rd < (NLAYERS > 1 ? 5 : 2); rd++) {
      if (rd >= 2 && warp >= 8) break;
      const int tk = rd < 2 ? blockIdx.x * 12 + warp : blockIdx.x * 8 + warp;
      const int half = tk & 1;
      const int blk = rd < 2 ? (tk >> 1) * 2 + rd : (rd == 2 ? 32 + (tk >> 1) : (tk >> 1) * 2 + rd - 3);
      const CUtensorMap* tm = rd < 2 ? &tm_wqA : (rd == 2 ? &tm_wqB : &tm_wf);
      const int j0 = (blk & 15) >> 1;
#define AUX_LOAD(n) { const uint32_t d_ = buf + ((n) & 1) * 8192, b_ = bar + ((n) & 1) * 8; const int r_ = kslice(j0, 2 * (n) + half) * 64; \
        mbar_expect_tx(b_, 8192); tma_load_2d(d_, tm, b_, blk * 64, r_); tma_load_2d(d_ + 4096, tm, b_, blk * 64, r_ + 32); }
      if (el) {
        if (rd == 3) { wait_flag(&g_flags.wfready[j0].v, ep1 * 16); fence_proxy_async_global(); }
        AUX_LOAD(0); AUX_LOAD(1);
      }
      __syncwarp();
      float cs[8][4];
#pragma unroll
      for (int i = 0; i < 8; i++) cs[i][0] = cs[i][1] = cs[i][2] = cs[i][3] = 0.f;
#pragma unroll 1
      for (int n = 0; n < 8; n++) {
        const uint32_t tb = buf + (n & 1) * 8192 + lrow;
        mbar_wait(bar + (n & 1) * 8, (n >> 1) & 1);
#pragma unroll
        for (int i = 0; i < 16; i++) {
          uint32_t b0, b1, b2, b3;
          ldsm_x4_t(tb + (i >> 2) * 2048 + (((i & 3) * 32 + lhi) ^ lsw), b0, b1, b2, b3);
          mma_bf16(cs[2 * (i & 3)], 0x3F803F80u, 0x3F803F80u, 0x3F803F80u, 0x3F803F80u, b0, b1);
          mma_bf16(cs[2 * (i & 3) + 1], 0x3F803F80u, 0x3F803F80u, 0x3F803F80u, 0x3F803F80u, b2, b3);
        }
        __syncwarp();
        if (el && n < 6) AUX_LOAD(n + 2);
        __syncwarp();
      }
      if (lane < 4) {
#pragma unroll
        for (int i = 0; i < 8; i++) st_b64(&g_colsum[rd >= 2][blk * 32 + i * 4 + lane][half], __float_as_uint(cs[i][0]), (__float_as_uint(cs[i][1]) & ~3u) | (ep1 & 3));
      }
      __syncwarp();
    }
  } else if (warp >= 8) {
    asm volatile("setmaxnreg.dec.sync.aligned.u32 40;");
    if (warp == 8) {
      const bool el = elect_one();
      cluster_wait();
      if (el) {
#pragma unroll 1
        for (int l = 0; l < NLAYERS; l++) {
          const uint32_t par = l & 1;
          const CUtensorMap* tqk = par ? &tm_wf : &tm_wqA;
          const CUtensorMap* tv = par ? &tm_wqB : &tm_wqA;
          const CUtensorMap* two = par ? &tm_woB : &tm_woA;
          if (l == 1) { LOAD_EPOCH(); wait_flag(&g_flags.wfready[jj].v, ep1 * 16); fence_proxy_async_global(); }
#pragma unroll 1
          for (int u = 0; u < 32; u++) {
            if (u >= 4) mbar_wait_sl(bar_done + (u - 4) * 8, par);
            else if (l) mbar_wait_sl(bar_done + (43 + u + (u >> 1)) * 8, par ^ 1);
            else if (u == 1) __nanosleep(STAG1);
            else if (u == 2) mbar_wait_sl(bar_full, 0);
            const uint32_t fb = bar_full + u * 8;
            const bool res = u < 4 ? (l || u >= 2) : (u < 11 || (u >= 18 && u < 22));
            mbar_expect_tx(fb, res ? QST : QST + SLOT);
            const int row = kslice(jj, u < 4 ? u & 1 : (u < 18 ? u - 2 : (u < 22 ? u - 6 : u - 20))) * 64 + (int)rank * 32;
            const int col = jj * 128 + (u < 4 ? u >> 1 : (u >= 18)) * 64;
            const uint32_t dst = sbase + (u & 3) * QST + rank * 4096;
            tma_load_2d_mc(dst, tqk, fb, col, row);
            tma_load_2d_mc(dst + 8192, tqk, fb, col + 1024, row);
            tma_load_2d_mc(dst + 16384, tv, fb, col + 2048, row);
            if (l == 0 && u < 4) PROFT(473 + u);
          }
#pragma unroll 1
          for (int s = 0; s < 16; s++) {
            if (s < 5) { if (s != 2 && s != 4) mbar_wait_sl(bar_done + (28 + s) * 8, par); }
            else if (s != 14) mbar_wait_sl(bar_done + (27 + s - (s == 15)) * 8, par);
            const uint32_t fb = bar_full + (32 + s) * 8;
            mbar_expect_tx(fb, (s && s < 8) ? 2 * SLOT : SLOT);
            tma_load_2d_mc(sbase + rank * 8192 + (uint32_t)((WO_BSLOT >> (4 * s)) & 15) * SLOT, two, fb, jj * 128 + (int)rank * 64, wslice(jj, s) * 64);
            if (s >= 5 && s < 8) {
              if (s == 5) { mbar_wait_sl(bar_full + 33 * 8, par); fence_proxy_async_global(); }
              tma_load_2d(sbase + (uint32_t)((WO_ASLOT >> (4 * s)) & 15) * SLOT, &tm_o, fb, wslice(jj, s) * 64, mm * 128);
            }
          }
        }
      }
      __syncwarp();
    } else if (warp == 9) {
      const bool el = elect_one();
      if (el) {
        PROFT(472);
        tma_load_2d(sbase + OFF_S, &tm_x0, bar_full, jj * 128, mm * 128);
        __nanosleep(STAG1);
        tma_load_2d(sbase + OFF_S + SLOT, &tm_x0, bar_full + 8, jj * 128 + 64, mm * 128);
      }
      __syncwarp();
      LOAD_EPOCH();
#pragma unroll 1
      for (int lp = 0; lp < 2 * NLAYERS; lp++) {
        const int l = lp >> 1, ph = lp & 1;
        const uint32_t par = l & 1;
        const __nv_bfloat16* pb = g_obuf + ph * 64 + (size_t)(mm * 128 + (ph ? 0 : S_LEN) + (lane & 7) * 16 + (jj & 1) * 8) * D_MODEL + (jj >> 1) * 16;
        const CUtensorMap* tm = lp ? &tm_o : &tm_x0;
        const int row = mm * 128 + ((ph || !l) ? 0 : S_LEN);
        const uint32_t bit = ph ? O_BIT(l) : X_BIT(l - 1);
        const uint32_t slots = ph ? (uint32_t)(WO_ASLOT >> 36) : 0x8769876u;
        uint32_t rdy = lp ? 0 : 0xFF;
        mbar_wait_sl(ph ? bar_epi : (l ? bar_done + 47 * 8 : bar_full), ph ? par : (l ? par ^ 1 : 0));
#pragma unroll 1
        for (int i = 0; i < 7; i++) {
          if (!((rdy >> i) & 1)) {
            const unsigned* pp = reinterpret_cast<const unsigned*>(pb + ((jj + i + 1 + ((lane >> 3) & (POLLW - 1))) & 7) * 128);
            if (i == 0) __nanosleep(POLL0);
            unsigned v0 = ld_relaxed(pp);
            __nanosleep(POLLGAP);
            unsigned v1 = ld_relaxed(pp);
            uint32_t no;
#pragma unroll 1
            for (int it = 0; it < (1 << 18); it++) {
              no = __ballot_sync(0xffffffffu, (v0 ^ bit) & 1);
              if (!(no & 0xFF)) break;
              v0 = ld_relaxed(pp);
              no = __ballot_sync(0xffffffffu, (v1 ^ bit) & 1);
              if (!(no & 0xFF)) break;
              v1 = ld_relaxed(pp);
            }
            rdy = ((1 | (no & 0xFF00 ? 0 : 2) | (no & 0xFF0000 ? 0 : 4) | (no >> 24 ? 0 : 8)) & ((1 << POLLW) - 1)) << i;
          }
          if (i >= (ph ? 2 : 4)) mbar_wait_sl(bar_done + (i + (ph ? 33 : 0)) * 8, par);
          if (el) {
            if (i == 0) PROFT(320 + l * 16 + ph * 2);
            mbar_expect_tx(bar_chk + i * 8, SLOT);
            tma_load_2d(sbase + ((slots >> (4 * i)) & 15) * SLOT, tm, bar_chk + i * 8, ((jj + i + 1) & 7) * 128 + ph * 64, row);
          }
          __syncwarp();
        }
        if (ph == 0 && el) {
          if (l) { wait_flag(&g_flags.xready[l][mm].v, ep1 * 8); fence_proxy_async_global(); }
#pragma unroll 1
          for (int u = 11; u < 34; u++) {
            if (u == 18) u = 22;
            mbar_wait_sl(bar_done + (u - 4) * 8, par);
            if (u == 32) mbar_expect_tx(bar_xr, 2 * SLOT);
            tma_load_2d(sbase + OFF_RA + (u & 3) * SLOT, tm, u < 32 ? bar_full + u * 8 : bar_xr, kslice(jj, u < 18 ? u - 2 : (u < 32 ? u - 20 : u - 32)) * 64, row);
            if (l == 0 && u < 16 && NLAYERS > 1) {
              if (u == 11) { mbar_expect_tx(bar_phi, SLOT + 8192); tma_load_2d(sbase + OFF_PHI, &tm_phi, bar_phi, 0, jj * 128); }
              else tma_load_2d(sbase + 12 * SLOT + (u - 12) * 4096, &tm_wqB, bar_phi, jj * 128 + ((u - 12) >> 1) * 64, mm * 64 + (u & 1) * 32);
            }
          }
          wait_flag(&g_flags.oready[l][mm].v, ep1 * 8);
          fence_proxy_async_global();
          PROFT(321 + l * 16);
#pragma unroll 1
          for (int s = 1; s < 5; s++) {
            if (s != 4) mbar_wait_sl(s == 3 ? bar_lx : bar_done + (29 + s) * 8, par);
            tma_load_2d(sbase + (uint32_t)((WO_ASLOT >> (4 * s)) & 15) * SLOT, &tm_o, bar_full + (32 + s) * 8, wslice(jj, s) * 64, mm * 128);
          }
        }
        __syncwarp();
      }
      cluster_wait();
    } else {
      const int hw = warp - 10;
      LOAD_EPOCH();
      const bool el = elect_one();
      cluster_wait();
      if (hw == 0) {
        mbar_wait_sl(bar_full + 8, 0);
        if (lane < 7) prefetch_tmap(lane == 0 ? &tm_os : lane == 1 ? &tm_o : lane == 2 ? &tm_wf : lane == 3 ? &tm_wqB : lane == 4 ? &tm_woA : lane == 5 ? &tm_woB : &tm_phi);
        if (lane < 4) asm volatile("prefetch.global.L2 [%0];" :: "l"(prm.wB_phi + jj * 4096 + mm * 256 + lane * 64));
#pragma unroll 1
        for (int i = 0; i < 8; i++) {
          asm volatile("prefetch.global.L2 [%0];" :: "l"(prm.wB_qkv + (size_t)(mm * 64 + (i & 3) * 16 + (lane >> 1)) * 3072 + (i >> 2) * 1024 + jj * 128 + (lane & 1) * 64));
          __nanosleep(PFGAP);
        }
      } else {
#pragma unroll 1
        for (int b = 0; b < 2; b++) {
          float4* z = reinterpret_cast<float4*>(g_kv[b] + (jj * 4) * KVH + mm * (4 * KVH / 16)) + lane;
#pragma unroll
          for (int i = 0; i < 5; i++) z[i * 32] = make_float4(0.f, 0.f, 0.f, 0.f);
        }
      }
      __syncwarp();
      uint32_t chkp = 0;
#pragma unroll 1
      for (int lp = 0; lp < 2 * NLAYERS; lp++) {
        const int l = lp >> 1, ph = lp & 1;
        const uint32_t par = l & 1;
        int lane; asm volatile("mov.u32 %0, %%laneid;" : "=r"(lane));
        if (hw) {
          const uint32_t bit = ph ? O_BIT(l) : X_BIT(l - 1);
          const uint32_t slots = ph ? (uint32_t)(WO_ASLOT >> 36) : 0x8769876u;
#pragma unroll 1
          for (int c = 0; c < 7; c++) {
            const uint32_t tile = sbase + ((slots >> (4 * c)) & 15) * SLOT;
#pragma unroll 1
            for (int it = 0; it < (1 << 12); it++) {
              mbar_wait_sl(bar_chk + c * 8, (chkp >> c) & 1);
              chkp ^= 1u << c;
              if (el && c == 0) PROFT(488 + lp);
              if (lp == 0) break;
              uint32_t a1 = 1, o1 = 0;
#pragma unroll
              for (int i = 0; i < 16; i++) {
                uint32_t w;
                asm volatile("ld.shared.u32 %0, [%1];" : "=r"(w) : "r"(tile + i * 1024 + (lane & 7) * 132 + (lane >> 3) * 32) : "memory");
                a1 &= w; o1 |= w;
              }
              if (__all_sync(0xffffffffu, ((bit ? a1 : ~o1) & 1) != 0)) break;
              if (el) {
                fence_proxy_async_smem();
                mbar_expect_tx(bar_chk + c * 8, SLOT);
                tma_load_2d(tile, &tm_o, bar_chk + c * 8, ((jj + c + 1) & 7) * 128 + ph * 64, mm * 128 + (ph ? 0 : S_LEN));
                RETRY_COUNT();
              }
              __syncwarp();
            }
            if (el) mbar_arrive_local(bar_full + (c + (ph ? 41 : 4)) * 8);
            __syncwarp();
          }
          if (ph) continue;
#pragma unroll 1
          for (int hp = 0; hp < 2; hp++) {
            const uint4* src = reinterpret_cast<const uint4*>(g_colsum[par][jj * 64 + hp * 32 + lane]);
            uint32_t bad;
            int it = 0;
            float c[6];
            do {
              bad = 0;
#pragma unroll
              for (int p = 0; p < 3; p++) {
                const uint4 v = ld_ll(src + p * 512);
                bad |= (v.y ^ ep1) | (v.w ^ ep1);
                c[2 * p] = __uint_as_float(v.x) + __uint_as_float(v.z); c[2 * p + 1] = __uint_as_float(v.y) + __uint_as_float(v.w);
              }
              bad &= 3;
              if (bad) __nanosleep(300);
            } while (bad && ++it < (1 << 16));
#pragma unroll
            for (int p = 0; p < 6; p++) {
              uint32_t h, m, lo;
              split3(c[p], h, m, lo);
              sts128(sbase + OFF_LNB + hp * 4096 + (p >> 1) * 1024 + lane * 32 + (p & 1) * 16, h | (m << 16), h | (lo << 16), h | (m << 16), lo | (m << 16));
            }
            fence_proxy_async_smem();
            __syncwarp();
            if (el) { mbar_arrive_local(hp ? bar_stat2 : bar_stat); if (hp == 0) PROFT(324 + l * 16); }
            __syncwarp();
          }
        } else if (ph == 0) {
          mbar_wait_sl(bar_done + 24, par);
          const uint4* sp = reinterpret_cast<const uint4*>(g_stats + (size_t)(mm * 128) * 8) + lane;
#pragma unroll 1
          for (int hf = 0; hf < 4; hf++) {
            uint4 v[4];
            uint32_t bad;
            int it = 0;
            do {
              bad = 0;
#pragma unroll
              for (int i = 0; i < 4; i++) { v[i] = ld_ll(sp + (hf * 4 + i) * 32); bad |= (v[i].y ^ STAT_TAG(l)) | (v[i].w ^ STAT_TAG(l)); }
              bad &= 3;
              if (bad) __nanosleep(200);
            } while (bad && ++it < (1 << 16));
            __syncwarp();
            float mean = 0.f, m2 = 0.f;
#pragma unroll
            for (int i = 0; i < 4; i++) {
              float a = __uint_as_float(v[i].x) + __uint_as_float(v[i].z);
              a += __shfl_xor_sync(0xffffffffu, a, 1); a += __shfl_xor_sync(0xffffffffu, a, 2);
              a *= 0.125f;
              const float e0 = __uint_as_float(v[i].x) - a, e1 = __uint_as_float(v[i].z) - a;
              float q = fmaf(fmaf(e0, e0, e1 * e1), 128.f, __uint_as_float(v[i].y) + __uint_as_float(v[i].w));
              q += __shfl_xor_sync(0xffffffffu, q, 1); q += __shfl_xor_sync(0xffffffffu, q, 2);
              if ((lane & 3) == i) { mean = a; m2 = q; }
            }
            const uint32_t row = hf * 32 + (lane & 3) * 8 + (lane >> 2);
            uint32_t h, m, lo;
            split3(-0.5f * mean, h, m, lo);
            sts128(sbase + OFF_LNA + row * 16, h | (h << 16), m | (h << 16), lo | (m << 16), m | (lo << 16));
            sts32f(sbase + OFF_ST + row * 4, rsqrtf(m2 * (1.f / 1024.f) + 1e-5f));
          }
          fence_proxy_async_smem();
          __syncwarp();
          if (el) { mbar_arrive_local(bar_stat); PROFT(323 + l * 16); }
          __syncwarp();
#pragma unroll 1
          for (int i = 0; i < 8 - 4 * l; i++) {
            asm volatile("prefetch.global.L2 [%0];" :: "l"(i < 4 ? (l ? prm.wB_o : prm.wA_o) + (size_t)cta * 8192 + i * 2048 + lane * 64
                                                                 : prm.wB_qkv + (size_t)(cta * 8 + (i - 4) * 2 + (lane >> 4)) * 3072 + 2048 + (lane & 15) * 64));
            __nanosleep(PFGAP);
          }
          continue;
        }
        if (hw) {
          if (l & 1) {
#pragma unroll 1
            for (int h = 0; h < 2; h++) {
              asm volatile("bar.sync %0, 288;" :: "r"(BAR_KV + h) : "memory");
              __syncwarp();
              PROFT(331 + l * 16 + h);
              if (lane < 16) signal_release(&g_flags.kvready[(l & 2) + h][jj][lane].v);
              const unsigned* kf = &g_flags.kvready[(l & 2) + h][jj][mm].v;
              unsigned v0 = ld_relaxed(kf);
              __nanosleep(150);
              unsigned v1 = ld_relaxed(kf);
#pragma unroll 1
              for (int it = 0; it < (1 << 18); it++) {
                if (v0 == ep1 * 16) break;
                v0 = ld_relaxed(kf);
                if (v1 == ep1 * 16) break;
                v1 = ld_relaxed(kf);
              }
              fence_acquire();
              __syncwarp();
              if (el) { mbar_arrive_local(bar_kvf + h * 8); PROFT(333 + l * 16 + h); }
              __syncwarp();
            }
          }
        } else {
#pragma unroll 1
          for (uint32_t ev = l == NLAYERS - 1 ? 0x80u : (l == 0 ? 0x836054u : 0x830u); ev != 8; ev >>= 4) {
            const int e = ev & 15;
            asm volatile("bar.sync %0, 288;" :: "r"((0xFECA987 >> (4 * e)) & 15) : "memory");
            if (el) {
              if (e < 4) {
                PROFT(325 + l * 16 + e);
                tma_store_2d(&tm_o, sbase + (e ? 11 : 12) * SLOT, jj * 128 + (e & 1) * 64, mm * 128 + (e ? S_LEN : 0));
              } else {
                if (e == 5) mbar_expect_tx(bar_phi + 8, SLOT);
#pragma unroll 1
                for (int i = 0; i < 4; i++) {
                  const uint32_t a = sbase + (e > 4 ? 10 : 12) * SLOT + i * 4096;
                  const int c0 = (e > 4 ? 1024 : 0) + jj * 128 + (i >> 1) * 64, c1 = mm * 64 + (i & 1) * 32;
                  if (e == 5) tma_load_2d(a, &tm_wqB, bar_phi + 8, c0, c1); else tma_store_2d(&tm_wf, a, c0, c1);
                }
                if (e != 5) {
                  asm volatile("cp.async.bulk.commit_group;\ncp.async.bulk.wait_group.read 0;" ::: "memory");
                  mbar_arrive_local(bar_phi + (e - 4) * 4);
                }
              }
              if ((0x49 >> e) & 1) {
                bulk_commit_wait();
                signal_release(e == 0 ? &g_flags.oready[l][mm].v : e == 6 ? &g_flags.wfready[jj].v : &g_flags.xready[l + 1][mm].v);
              }
              if (e == 3) PROFT(330 + l * 16);
              if (e == 6) PROFT(335);
            }
            __syncwarp();
          }
        }
      }
    }
    cluster_sync();
  } else {
    asm volatile("setmaxnreg.inc.sync.aligned.u32 232;");
    LOAD_EPOCH();
    const int wg = warp >> 2;
    const int r0 = warp * 16;
    const uint32_t pK = sbase + OFF_S, pV = sbase + OFF_S + SLOT;
#define PMASKS(on, bit) const uint32_t pm0 = ((on) && t == (g & 3) && (g >> 2) == (g & 1)), pm1 = ((on) && t == (g & 3) && (g >> 2) != (g & 1)), pbit = (bit)
#define PBIT0(w) (((w) & ~pm0) | (pbit & pm0))
#define PBIT1(w) (((w) & ~pm1) | (pbit & pm1))
#define LANE_CONSTS() \
    int lane; asm volatile("mov.u32 %0, %%laneid;" : "=r"(lane)); \
    const int g = lane >> 2, t = lane & 3; \
    const uint32_t srowoff = (r0 + (lane & 15)) * 128, lsw = (lane & 7) << 4, lhi = (lane >> 4) << 4, lsw2 = (lane & 6) << 3; \
    (void)g; (void)t; (void)srowoff; (void)lsw; (void)lhi; (void)lsw2;
    uint32_t stgp = 0, peer;
    asm volatile("mapa.shared::cluster.u32 %0, %1, %2;" : "=r"(peer) : "r"(sbase), "r"(rank ^ 1));
    peer -= sbase;
    const uint32_t dA0 = (((sbase & 0x3FFFF) + wg * 8192) >> 4) | 0x10000u, dB0 = ((sbase & 0x3FFFF) >> 4) | 0x2000000u;
    cluster_wait();
#define STG_ARRIVE() { __syncwarp(); if (elect_one()) mbar_arrive_local(bar_stg); }
#define STG_WAIT() { mbar_wait(bar_stg, stgp); stgp ^= 1; }
#define PROFS() do {} while (0)
#define REL(addr) { if (elect_one()) { mbar_arrive_local(addr); asm volatile("mbarrier.arrive.shared::cluster.b64 _, [%0];" :: "r"((addr) + peer) : "memory"); } }
#define QSTEP(ACC, DA, SC, PRE) { \
      const uint32_t da = (DA), db = dB0 + (ub & 0x18) * (QST >> 7); \
      mbar_wait(ub, par); \
      PRE; \
      wgmma_fence(); \
      wgmma4_n192<SC>(ACC, da, db); \
      wgmma_commit(); PROFS(); }
#define QREL() { wgmma_wait<1>(); REL(ub + 376); ub += 8; }
#define RA_CUR (dA0 + (OFF_RA >> 4) + (ub & 0x18) * (SLOT >> 7))
#define PUMP1() { QSTEP(S1, RA_CUR, 1, {}); QREL(); }
#define PUMP0() { PUMP1(); SCHED_FENCE(); }
#define PUMP() if (h == 0) PUMP1()
#define WSTEP() { \
      const uint32_t s4 = (ub - bar_full - 256) >> 1; \
      const uint32_t da = dA0 + (((uint32_t)(WO_ASLOT >> s4) & 15) << 10), db = dB0 + (((uint32_t)(WO_BSLOT >> s4) & 15) << 10); \
      mbar_wait(ub, par); \
      wgmma_fence(); \
      wgmma4_n128<1>(S1, da, db); \
      wgmma_commit(); PROFS(); \
      wgmma_wait<1>(); \
      if (s4) REL(ub + 376); \
      ub += 8; }
#define PUMPS(n) { _Pragma("unroll 1") for (int i_ = 0; i_ < (n); i_++) PUMP1(); }
#define SITE(n) { if ((BMASK >> (n)) & 1) { PUMP(); } else SCHED_FENCE(); }
#define LNSTEP(ACC, hh) { wgmma_fence(); wgmma_n192<1, 0>(ACC, make_desc(sbase + OFF_LNA + wg * 1024, 0, 128) ^ (1ull << 62), make_desc(sbase + OFF_LNB + (hh) * 4096, 0, 128) ^ (1ull << 62)); }
#define DRAIN_A(ACC, PMP) { \
      LANE_CONSTS(); \
      STAGE64(ACC, 64, pV, 1, 1); \
      PMP; \
      STAGE64(ACC, 32, pK, 0, 1); \
      STG_ARRIVE(); \
      _Pragma("unroll") for (int i_ = 0; i_ < 16; i_++) qa[i_] = pack_bf16(ACC[2 * i_], ACC[2 * i_ + 1]); \
      PINU(qa, 16); }
#define DRAIN_B(ACC) { \
      LANE_CONSTS(); \
      STAGE64(ACC, 64, pV, 1, 0); \
      _Pragma("unroll") for (int i_ = 0; i_ < 64; i_++) st[i_] = ACC[i_]; \
      PIN(st, 64); }
#define WARP_STORE(tm, tile, col, row) { fence_proxy_async_smem(); __syncwarp(); \
      if (elect_one()) { tma_store_2d(tm, (tile) + r0 * 128, col, (row) + r0); asm volatile("cp.async.bulk.commit_group;" ::: "memory"); } __syncwarp(); }
#define PUBLISH_O() { if (h) WARP_STORE(&tm_os, pO, jj * 128 + 64, mm * 128) else { fence_proxy_async_smem(); bar_arrive<BAR_O, 288>(); } }
#define X_OUT(pc, on) { \
      PMASKS(on, X_BIT(l)); \
      _Pragma("unroll") for (int j = (pc) * 4; j < (pc) * 4 + 4; j++) \
        stsm_x4(pK + (pc) * SLOT + srowoff + ((((uint32_t)(j & 3) << 5) + lhi) ^ lsw), \
                PBIT0(pack_bf16(S1[j * 8 + 0], S1[j * 8 + 1])), PBIT0(pack_bf16(S1[j * 8 + 2], S1[j * 8 + 3])), \
                PBIT1(pack_bf16(S1[j * 8 + 4], S1[j * 8 + 5])), PBIT1(pack_bf16(S1[j * 8 + 6], S1[j * 8 + 7]))); }
#define REST_P1(SKEW) { \
      mbar_wait(bar_stat2, par); \
      LNSTEP(S1, 1); \
      _Pragma("unroll 1") while (ub < bar_full + 256) { \
        if (ub == bar_full + 256 - 8 * (SKEW) && wg == 0) bar_sync<BAR_SKEW, 256>(); \
        QSTEP(S1, RA_CUR, 1, {}); \
        if (ub == bar_full + 248 && wg == 1) bar_arrive<BAR_SKEW, 256>(); \
        QREL(); \
      } \
      hbase += 256; \
      mbar_wait(bar_done + (31 - (SKEW)) * 8, par);        \
      wgmma_wait<0>(); \
      ACC_FENCE(S1, 96); \
      REL(bar_done + 31 * 8); \
      PROF(13); }
#define FOLD(tile, rd) { \
          LANE_CONSTS(); \
          float d[32]; \
          ACC_DEF(d, 32); \
          mbar_wait(bar_phi + (rd) * 8, 0); \
          wgmma_fence(); \
          _Pragma("unroll") for (int i = 0; i < 2; i++) { \
            const uint64_t da = make_desc((tile) + wg * 8192 + i * 64, 16, 1024); \
            const uint64_t db = make_desc(sbase + OFF_PHI + wg * 4096 + i * 2048, 16, 512) ^ (3ull << 62); \
            wgmma_n32<0>(d + i * 16, da, db); wgmma_n32<1>(d + i * 16, da + 2, db + 64); \
          } \
          wgmma_commit(); \
          PUMP0(); \
          ACC_FENCE(d, 32); \
          bar_wg(wg); \
          _Pragma("unroll") for (int i = 0; i < 4; i++) { \
            const float* x = d + (i & 1) * 8 + (i >> 1) * 2; \
            sts128((tile) + wg * 8192 + ((warp & 3) * 16 + (i >> 1) * 8 + g) * 128 + (((2 * t + (i & 1)) ^ g) << 4), \
                   pack_bf16(x[0], x[1]), pack_bf16(x[4], x[5]), pack_bf16(x[16], x[17]), pack_bf16(x[20], x[21])); \
          } \
          fence_proxy_async_smem(); \
          bar_arrive<BAR_WF + 3 * (rd), 288>(); }
#define LOAD_X0(base) \
      _Pragma("unroll") for (int j = 0; j < 8; j++) { \
        uint32_t x0, x1, x2, x3; \
        ldsm_x4((base) + (j >> 2) * SLOT + srowoff + ((((uint32_t)(j & 3) << 5) + lhi) ^ lsw), x0, x1, x2, x3); \
        S1[j * 8 + 0] = bf_lo(x0); S1[j * 8 + 1] = bf_hi(x0); S1[j * 8 + 2] = bf_lo(x1); S1[j * 8 + 3] = bf_hi(x1); \
        S1[j * 8 + 4] = bf_lo(x2); S1[j * 8 + 5] = bf_hi(x2); S1[j * 8 + 6] = bf_lo(x3); S1[j * 8 + 7] = bf_hi(x3); \
      }
#define LOAD_X() { \
      wgmma_wait<0>(); \
      mbar_wait(bar_xr, par); \
      LOAD_X0(sbase + OFF_RA); \
      ACC_FENCE(S1, 64); \
      __syncwarp(); if (elect_one()) mbar_arrive_local(bar_lx); }

    float S1[96];
#pragma unroll
    for (int i = 0; i < 64; i++) S1[i] = 0.f;
#pragma unroll 1
    for (int l = 0; l < NLAYERS; l++) {
      const uint32_t par = l & 1;
      bar_wg(wg);
      PROF(0);
      uint32_t ub = bar_full;
      const bool hsend = (warp == 7) && (mm < 15);
      const uint32_t hbit = (NLAYERS > 2) ? (l == 0) : (ep1 & 1);
      float S0[96];
      {
        LANE_CONSTS();
        ACC_DEF(S0, 96);
        QSTEP(S0, dA0 + (OFF_S >> 4), 0, {});
        ub += 8;
        PROF(1);
        if (l == 0) { mbar_wait(ub, 0); LOAD_X0(pK); }
        else { X_OUT(1, false); fence_proxy_async_smem(); }
        SCHED_FENCE();
        {
          float a0 = S1[0], a1 = S1[2], b0 = S1[1], b1 = S1[3];
#pragma unroll
          for (int i = 4; i < 64; i += 4) { a0 += S1[i]; b0 += S1[i + 1]; a1 += S1[i + 2]; b1 += S1[i + 3]; }
          a0 += b0; a1 += b1;
          a0 += __shfl_xor_sync(0xffffffffu, a0, 1); a1 += __shfl_xor_sync(0xffffffffu, a1, 1);
          a0 += __shfl_xor_sync(0xffffffffu, a0, 2); a1 += __shfl_xor_sync(0xffffffffu, a1, 2);
          a0 *= (1.f / 128.f); a1 *= (1.f / 128.f);
          asm volatile("" : "+f"(a0), "+f"(a1));
          bar_wg(wg);
          QSTEP(S0, dA0 + ((OFF_S + SLOT) >> 4), 1, wgmma_wait<0>());
          REL(ub + 376); ub += 8;
          SCHED_FENCE();
          float q0 = 0.f, q1 = 0.f;
          b0 = 0.f; b1 = 0.f;
#pragma unroll
          for (int i = 0; i < 64; i += 4) {
            const float d0 = S1[i] - a0, d1 = S1[i + 1] - a0, d2 = S1[i + 2] - a1, d3 = S1[i + 3] - a1;
            q0 = fmaf(d0, d0, q0); b0 = fmaf(d1, d1, b0); q1 = fmaf(d2, d2, q1); b1 = fmaf(d3, d3, b1);
          }
          q0 += b0; q1 += b1;
          q0 += __shfl_xor_sync(0xffffffffu, q0, 1); q1 += __shfl_xor_sync(0xffffffffu, q1, 1);
          q0 += __shfl_xor_sync(0xffffffffu, q0, 2); q1 += __shfl_xor_sync(0xffffffffu, q1, 2);
          if (t < 2) st_b64(g_stats + (size_t)(mm * 128 + r0 + g + t * 8) * 8 + jj, __float_as_uint(t ? a1 : a0), (__float_as_uint(t ? q1 : q0) & ~3u) | STAT_TAG(l));
        }
        if (l) { asm volatile("cp.async.bulk.wait_group 0;" ::: "memory"); bar_arrive<BAR_O + 3, 288>(); }
        ACC_DEF(S1, 96);
        QSTEP(S1, dA0 + (OFF_S >> 4), 0, {});
        QREL();
        QSTEP(S1, dA0 + ((OFF_S + SLOT) >> 4), 1, {});
        QREL();
#pragma unroll 1
        for (int i = 0; i < 14; i++) {
          QSTEP(S0, RA_CUR, 1, {});
          if (i == 0) PROF(2);
          QREL();
        }
      }
      LANE_CONSTS();
      uint4* hbase = g_halo + (size_t)(mm * 8 + jj) * 512;
      mbar_wait(bar_stat, par);
      LNSTEP(S0, 0);
      wgmma_commit();
      const float rs0 = lds32f(sbase + OFF_ST + (r0 + g) * 4), rs1 = lds32f(sbase + OFF_ST + (r0 + g + 8) * 4);
      PUMP0();
      ACC_FENCE(S0, 96);
      PROF(3);
      if (!par) {
        constexpr uint32_t par = 0;
        uint32_t qa[16];
        DRAIN_A(S0, PUMP0());
#pragma unroll 1
        for (int h = 0; h < 2; h++) {
          const uint32_t pO = sbase + (h ? 3 : 12) * SLOT;
          PROF(4 + h * 12);
          const bool fold = (l == 0 && h == 0 && NLAYERS > 1);
          if (fold) FOLD(pO, 0) else if (h == 0) PUMPS(HPUMP1);
          LANE_CONSTS();
          uint4 hv[8];
#pragma unroll
          for (int i = 0; i < 8; i++) hv[i] = make_uint4(hbit, 0, 0, 0);
          const bool hrec = (warp == 0 && mm > 0);
          if (hrec) {
#pragma unroll
            for (int i = 0; i < 8; i++) hv[i] = ld_b128(hbase + lane - 8 * 512 + i * 32);
          }
          if (h) LOAD_X() else PUMPS(HPUMP2);
          const uint32_t halo = sbase + OFF_HALO;
          STG_WAIT();
          if (warp == 0) {
#pragma unroll 1
            for (int it = 0; it < (1 << 16); it++) {
              uint32_t bad = 0;
#pragma unroll
              for (int i = 0; i < 8; i++) bad |= hv[i].x ^ hbit;
              if (__all_sync(0xffffffffu, (bad & 1) == 0)) break;
#pragma unroll
              for (int i = 0; i < 8; i++) hv[i] = ld_b128(hbase + lane - 8 * 512 + i * 32);
            }
#pragma unroll
            for (int i = 0; i < 8; i++)
              stsm_x4(i < 4 ? halo + srowoff + ((((uint32_t)i << 5) + lhi) ^ lsw)
                            : halo + (srowoff >> 1) + (i >> 1) * 1024 + ((((uint32_t)(i & 1) << 5) + lhi) ^ lsw2), hv[i].x, hv[i].y, hv[i].z, hv[i].w);
            __syncwarp();
          }
          PROF(5 + h * 12);
          const uint32_t kb1 = pK + r0 * 128, vb1 = pV + r0 * 64;
          const uint32_t kb0 = r0 ? kb1 - 2048 : halo, vb0 = r0 ? vb1 - 1024 : halo + 2048;
          const uint32_t vhs = r0 ? 8192 : 1024;
          float s[2][4][4];
          {
            uint32_t kf[2][4][4];
#pragma unroll
            for (int i = 0; i < 8; i++) {
              const int hh = i >> 2, jb = i & 3;
              ldsm_x4(((jb < 2) ? kb0 : kb1) + ((jb & 1) * 8 + (lane & 7)) * 128 + ((hh * 64 + ((lane >> 3) << 4)) ^ lsw), kf[hh][jb][0], kf[hh][jb][1], kf[hh][jb][2], kf[hh][jb][3]);
              s[hh][jb][0] = s[hh][jb][1] = s[hh][jb][2] = s[hh][jb][3] = 0.f;
            }
#pragma unroll
            for (int ks = 0; ks < 2; ks++)
#pragma unroll
              for (int i = 0; i < 8; i++) {
                const int hh = i >> 2, jb = i & 3;
                mma_bf16(s[hh][jb], qa[hh * 8 + ks * 4], qa[hh * 8 + ks * 4 + 1], qa[hh * 8 + ks * 4 + 2], qa[hh * 8 + ks * 4 + 3], kf[hh][jb][ks * 2], kf[hh][jb][ks * 2 + 1]);
              }
          }
          PUMP();
          if (fold) bar_arrive<BAR_WF + 2, 288>();
          PROF(6 + h * 12);
          const bool e = g & 1, hb = (2 * t + (g & 1)) <= g;
          uint32_t vf[2][2][2][4];
#pragma unroll
          for (int i = 0; i < 8; i++) {
            const int hh = i >> 2, ks = (i >> 1) & 1, dp = i & 1;
            ldsm_x4_t((ks ? vb1 + hh * 8192 : vb0 + hh * vhs) + (lane & 15) * 64 + ((dp * 32 + lhi) ^ lsw2), vf[hh][ks][dp][0], vf[hh][ks][dp][1], vf[hh][ks][dp][2], vf[hh][ks][dp][3]);
          }
          float va[2][2], vb[2][2], mx[2][2];
#pragma unroll
          for (int hh = 0; hh < 2; hh++) {
            va[hh][0] = e ? s[hh][1][1] : s[hh][1][0];
            vb[hh][0] = hb ? (e ? s[hh][2][1] : s[hh][2][0]) : (e ? s[hh][0][1] : s[hh][0][0]);
            va[hh][1] = e ? s[hh][2][3] : s[hh][2][2];
            vb[hh][1] = hb ? (e ? s[hh][3][3] : s[hh][3][2]) : (e ? s[hh][1][3] : s[hh][1][2]);
          }
          if (warp == 0 && mm == 0) {
#pragma unroll
            for (int hh = 0; hh < 2; hh++) { va[hh][0] = -INFINITY; if (!hb) { vb[hh][0] = -INFINITY; vb[hh][1] = -INFINITY; } }
          }
#pragma unroll
          for (int i = 0; i < 4; i++) mx[i >> 1][i & 1] = fmaxf(va[i >> 1][i & 1], vb[i >> 1][i & 1]);
#pragma unroll
          for (int o = 1; o <= 2; o <<= 1)
#pragma unroll
            for (int i = 0; i < 4; i++) mx[i >> 1][i & 1] = fmaxf(mx[i >> 1][i & 1], __shfl_xor_sync(0xffffffffu, mx[i >> 1][i & 1], o));
          const float sc0 = rs0 * (0.17677669529663687f * LOG2E), sc1 = rs1 * (0.17677669529663687f * LOG2E);
#pragma unroll
          for (int i = 0; i < 4; i++) {
            const float sc = (i & 1) ? sc1 : sc0, m = mx[i >> 1][i & 1];
            va[i >> 1][i & 1] = ex2((va[i >> 1][i & 1] - m) * sc); vb[i >> 1][i & 1] = ex2((vb[i >> 1][i & 1] - m) * sc);
            mx[i >> 1][i & 1] = va[i >> 1][i & 1] + vb[i >> 1][i & 1];
          }
          if (h == 0 && ASITE) { PIN(&va[0][0], 4); PIN(&vb[0][0], 4); PIN(&mx[0][0], 4); PUMP1(); }
#pragma unroll
          for (int o = 1; o <= 2; o <<= 1)
#pragma unroll
            for (int i = 0; i < 4; i++) mx[i >> 1][i & 1] += __shfl_xor_sync(0xffffffffu, mx[i >> 1][i & 1], o);
          const uint32_t selA = e ? 0x1044 : 0x4410, selB = e ? 0x3244 : 0x4432, selL = hb ? 0x4444 : selB, selH = hb ? selB : 0x4444;
          float o[2][4][4];
          uint32_t pa[2][6];
#pragma unroll
          for (int hh = 0; hh < 2; hh++) {
            const float i0 = rcp_fast(mx[hh][0]), i1 = rcp_fast(mx[hh][1]);
            const uint32_t w0 = pack_bf16(va[hh][0] * i0, vb[hh][0] * i0), w1 = pack_bf16(va[hh][1] * i1, vb[hh][1] * i1);
            pa[hh][0] = __byte_perm(w0, 0, selL); pa[hh][1] = __byte_perm(w0, 0, selA); pa[hh][2] = __byte_perm(w1, 0, selL);
            pa[hh][3] = __byte_perm(w0, 0, selH); pa[hh][4] = __byte_perm(w1, 0, selA); pa[hh][5] = __byte_perm(w1, 0, selH);
#pragma unroll
            for (int dj = 0; dj < 4; dj++) { o[hh][dj][0] = o[hh][dj][1] = o[hh][dj][2] = o[hh][dj][3] = 0.f; }
          }
          PROF(7 + h * 12);
#pragma unroll
          for (int i = 0; i < 8; i++) mma_bf16(o[i >> 2][i & 3], pa[i >> 2][0], 0u, pa[i >> 2][1], pa[i >> 2][2], vf[i >> 2][0][(i >> 1) & 1][(i & 1) * 2], vf[i >> 2][0][(i >> 1) & 1][(i & 1) * 2 + 1]);
#pragma unroll
          for (int i = 0; i < 8; i++) mma_bf16(o[i >> 2][i & 3], pa[i >> 2][3], pa[i >> 2][4], 0u, pa[i >> 2][5], vf[i >> 2][1][(i >> 1) & 1][(i & 1) * 2], vf[i >> 2][1][(i >> 1) & 1][(i & 1) * 2 + 1]);
          if (h == 0) PUMP1() else mbar_wait(bar_done + 30 * 8, par);
          if (fold) mbar_wait(bar_phi, 1);
#pragma unroll
          for (int i = 0; i < 4; i++) {
            const int hh = i >> 1, dp = i & 1;
            PMASKS(h, O_BIT(l));
            stsm_x4(pO + srowoff + ((hh * 64 + dp * 32 + lhi) ^ lsw), PBIT0(pack_bf16(o[hh][dp * 2][0], o[hh][dp * 2][1])), PBIT0(pack_bf16(o[hh][dp * 2][2], o[hh][dp * 2][3])),
                    PBIT1(pack_bf16(o[hh][dp * 2 + 1][0], o[hh][dp * 2 + 1][1])), PBIT1(pack_bf16(o[hh][dp * 2 + 1][2], o[hh][dp * 2 + 1][3])));
          }
          PUBLISH_O();
          PROF(11 + h * 12);
          if (h) break;
          if (fold) { PUMPS(FPUMP); FOLD(pK, 1); }
          REST_P1(ASKEW);
          if (fold) mbar_wait(bar_phi + 8, 1);
          DRAIN_A(S1, {});
        }
      } else {
        constexpr uint32_t par = 1;
        float st[64];
        DRAIN_B(S0);
        if (warp < 2) sts128(sbase + OFF_ONES + warp * 512 + lane * 16, 0x3F803F80u, 0x3F803F80u, 0x3F803F80u, 0x3F803F80u);
        const float c0 = rs0 * LOG2E, c1 = rs1 * LOG2E;
#pragma unroll 1
        for (int h = 0; h < 2; h++) {
          const uint32_t pO = sbase + (h ? 3 : 12) * SLOT;
          PROF(4 + h * 12);
          SITE(0);
          LANE_CONSTS();
          const uint32_t dsw = (uint32_t)(g ^ (2 * t)) << 4;
          const float* pk = st + 32;
          float4* kvg = reinterpret_cast<float4*>(g_kv[l >> 1] + (jj * 4 + h * 2 + wg) * KVH) + (warp & 3) * 32 + lane;
          const uint32_t dst = ((t & 2) ? pK : pO) + (r0 + g) * 128;
          float mq[4];
          {
            float e[16], f[16];
            float mn0 = rmin16(pk);
            asm volatile("" : "+f"(mn0)); SCHED_FENCE();
            float sa = exps16(e, pk, -c0, mn0 * c0), mx0 = rmax16(pk);
            asm volatile("" : "+f"(sa), "+f"(mx0)); PIN(e, 16); SITE(1);
            store16(e, sa, dst, dsw, 4);
            float sb = exps16(f, pk, c0, -mx0 * c0), mn1 = rmin16(pk + 2);
            asm volatile("" : "+f"(sb), "+f"(mn1)); PIN(f, 16); SITE(2);
            store16(f, sb, dst, dsw, 0);
            float sc = exps16(e, pk + 2, -c1, mn1 * c1), mx1 = rmax16(pk + 2);
            asm volatile("" : "+f"(sc), "+f"(mx1)); PIN(e, 16); SITE(3);
            store16(e, sc, dst + 1024, dsw, 4);
            float sd = exps16(f, pk + 2, c1, -mx1 * c1);
            asm volatile("" : "+f"(sd)); PIN(f, 16); SITE(4);
            store16(f, sd, dst + 1024, dsw, 0);
          }
          fence_proxy_async_smem();
          STG_ARRIVE();
          PROF(5 + h * 12);
          uint32_t fq[32];
          {
            float kv[20];
            ACC_DEF(kv, 20);
            const uint64_t dp = make_desc(wg ? pK : pO, 16, 1024);
            const uint64_t dv = (make_desc(pV + wg * 8192, OFF_ONES - OFF_S - SLOT - wg * 8192, 512) ^ (3ull << 62));
            constexpr uint64_t DVS = 64ull - (64ull << 16);
            STG_WAIT();
            wgmma_fence();
#pragma unroll
            for (int ks = 0; ks < 8; ks++) { if (ks == 0) wgmma_n40<0, 1>(kv, dp, dv); else wgmma_n40<1, 1>(kv, dp + ks * 128, dv + ks * DVS); }
            wgmma_commit();
            SCHED_FENCE();
            mq[0] = rmin16(st); mq[1] = rmax16(st);
            asm volatile("" : "+f"(mq[0]), "+f"(mq[1]));
            if (h == 0) PUMP1() else wgmma_wait<0>();
            ACC_FENCE(kv, 20);
#pragma unroll
            for (int i = 0; i < 4; i++) red_v4(reinterpret_cast<float*>(kvg + i * 128), kv[i * 4], kv[i * 4 + 1], kv[i * 4 + 2], kv[i * 4 + 3]);
            if (t == 0) red_v4(reinterpret_cast<float*>(kvg + 512), kv[16], kv[17], kv[18], kv[19]);
            asm volatile("bar.arrive %0, 288;" :: "r"(BAR_KV + h) : "memory");
            STG_ARRIVE();
          }
          PROF(6 + h * 12);
          expp16(fq, st, -c0, mq[0] * c0);
          mq[2] = rmin16(st + 2);
          PINU(fq, 8); asm volatile("" : "+f"(mq[2])); SITE(6);
          expp16(fq + 8, st, c0, -mq[1] * c0);
          mq[3] = rmax16(st + 2);
          PINU(fq + 8, 8); asm volatile("" : "+f"(mq[3])); SITE(7);
          STG_WAIT();
#pragma unroll
          for (int i = 0; i < 4; i++) sts128(dst + (((((i & 2) ? 0 : 4) + (i & 1)) << 4) ^ dsw), fq[i * 4], fq[i * 4 + 1], fq[i * 4 + 2], fq[i * 4 + 3]);
          expp16(fq + 16, st + 2, -c1, mq[2] * c1);
          PINU(fq + 16, 8); SITE(8);
          expp16(fq + 24, st + 2, c1, -mq[3] * c1);
#pragma unroll
          for (int i = 4; i < 8; i++) sts128(dst + 1024 + (((((i & 2) ? 0 : 4) + (i & 1)) << 4) ^ dsw), fq[i * 4], fq[i * 4 + 1], fq[i * 4 + 2], fq[i * 4 + 3]);
          PROF(7 + h * 12);
          if (h == 0) PUMPS(KVPUMP) else {
            LOAD_X();
#pragma unroll 1
            for (int i = 0; i < KVWO; i++) WSTEP();
          }
          PROF(8 + h * 12);
          {
            mbar_wait(bar_kvf + h * 8, l >> 1);
            PROF(9 + h * 12);
            float4 v[5];
#pragma unroll
            for (int i = 0; i < 4; i++) v[i] = __ldcg(kvg + i * 128);
            v[4] = __ldcg(kvg + 512 - t);
            if (h == 0) PUMPS(KVPUMP2);
            const uint32_t kd = pV + wg * 8192 + ((warp & 3) * 16 + (lane & 15)) * 128;
#pragma unroll
            for (int i = 0; i < 2; i++) {
              const float4 a = v[i * 2], b = v[i * 2 + 1];
              stsm_x4(kd + ((i * 32 + lhi) ^ lsw), pack_bf16(a.x, a.y), pack_bf16(a.z, a.w), pack_bf16(b.x, b.y), pack_bf16(b.z, b.w));
            }
            stsm_x4(kd + ((64u + lhi) ^ lsw), pack_bf16(v[4].x, 1.f), pack_bf16(v[4].z, 1.f), 0u, 0u);
          }
          fence_proxy_async_smem();
          STG_ARRIVE();
          float o[4][20];
          ACC_DEF(o[0], 20); ACC_DEF(o[1], 20); ACC_DEF(o[2], 20); ACC_DEF(o[3], 20);
          STG_WAIT();
          PROF(10 + h * 12);
          wgmma_fence();
#pragma unroll
          for (int hh = 0; hh < 2; hh++) {
            const uint64_t da = make_desc((hh ? pK : pO) + wg * 8192, 16, 1024);
            const uint64_t db = make_desc(pV + hh * 8192, 16, 1024);
#pragma unroll
            for (int ks = 0; ks < 4; ks += 2) { wgmma_n40<0, 0>(o[hh * 2 + (ks >> 1)], da + ks * 2, db + ks * 128); wgmma_n40<1, 0>(o[hh * 2 + (ks >> 1)], da + ks * 2 + 2, db + ks * 128 + 128); }
          }
          wgmma_commit();
          if (h == 0) PUMP1() else wgmma_wait<0>();
          ACC_FENCE(o[0], 20); ACC_FENCE(o[1], 20); ACC_FENCE(o[2], 20); ACC_FENCE(o[3], 20);
          bar_wg(wg);
          PMASKS(h, O_BIT(l));
#pragma unroll
          for (int hh = 0; hh < 2; hh++) {
            const float* x = o[hh * 2];
            const float* y = o[hh * 2 + 1];
            const float rx0 = rcp_fast(x[17]), ry0 = rcp_fast(y[17]), rx1 = rcp_fast(x[19]), ry1 = rcp_fast(y[19]);
            const float i0 = rcp_fast(fmaf(x[16], rx0, y[16] * ry0) + 1e-6f), i1 = rcp_fast(fmaf(x[18], rx1, y[18] * ry1) + 1e-6f);
            const float ax0 = rx0 * i0, ay0 = ry0 * i0, ax1 = rx1 * i1, ay1 = ry1 * i1;
#pragma unroll
            for (int dp = 0; dp < 2; dp++)
              stsm_x4(pO + srowoff + ((hh * 64 + dp * 32 + lhi) ^ lsw),
                      PBIT0(pack_bf16(fmaf(x[dp * 8], ax0, y[dp * 8] * ay0), fmaf(x[dp * 8 + 1], ax0, y[dp * 8 + 1] * ay0))),
                      PBIT0(pack_bf16(fmaf(x[dp * 8 + 2], ax1, y[dp * 8 + 2] * ay1), fmaf(x[dp * 8 + 3], ax1, y[dp * 8 + 3] * ay1))),
                      PBIT1(pack_bf16(fmaf(x[dp * 8 + 4], ax0, y[dp * 8 + 4] * ay0), fmaf(x[dp * 8 + 5], ax0, y[dp * 8 + 5] * ay0))),
                      PBIT1(pack_bf16(fmaf(x[dp * 8 + 6], ax1, y[dp * 8 + 6] * ay1), fmaf(x[dp * 8 + 7], ax1, y[dp * 8 + 7] * ay1))));
            if (hh == 0 && ((BMASK >> 9) & 1)) PUMP();
          }
          PUBLISH_O();
          PROF(11 + h * 12);
          if (h) break;
          REST_P1(1);
          DRAIN_B(S1);
        }
      }
      __syncwarp();
      if (elect_one()) mbar_arrive_local(bar_epi);
      bar_wg(wg);
#pragma unroll 1
      while (ub < bar_full + 384) {
        WSTEP();
        if (ub == bar_full + 8 * 41) { asm volatile("cp.async.bulk.wait_group.read 0;" ::: "memory"); PROF(35); }
        if (ub == bar_full + 8 * 42) PROF(36);
      }
      wgmma_wait<0>();
      ACC_FENCE(S1, 64);
      REL(bar_done + 47 * 8);
      PROF(37);
      {
        LANE_CONSTS();
        X_OUT(0, l < NLAYERS - 1);
        WARP_STORE(l < NLAYERS - 1 ? &tm_os : &tm_xo, pK, jj * 128, mm * 128 + (l < NLAYERS - 1 ? S_LEN : 0));
        if (l == NLAYERS - 1) {
          X_OUT(1, false);
          WARP_STORE(&tm_xo, pV, jj * 128 + 64, mm * 128);
          asm volatile("cp.async.bulk.wait_group 0;" ::: "memory");
        }
      }
#pragma unroll
      for (int i = 32; i < 64; i++) { uint32_t c; asm volatile("mov.b32 %0, %1;" : "=r"(c) : "f"(S1[i])); S1[i] = __uint_as_float(c); }
      PROF(38);
    }
    const int tid = threadIdx.x;
    if (tid == 0) {
      unsigned old = atomicAdd(&g_flags.done.v, 1);
      if (old == ep1 * NMAIN - 1) {
        asm volatile("st.relaxed.gpu.global.u32 [%0], %1;" :: "l"(&g_flags.epoch.v), "r"(ep1) : "memory");
      }
    }
    __syncwarp();
    cluster_sync();
  }
}

typedef CUresult (*PFN_encode)(CUtensorMap*, CUtensorMapDataType, cuuint32_t, void*, const cuuint64_t*, const cuuint64_t*,
                               const cuuint32_t*, const cuuint32_t*, CUtensorMapInterleave, CUtensorMapSwizzle,
                               CUtensorMapL2promotion, CUtensorMapFloatOOBfill);

CUtensorMap make_map(PFN_encode enc, const void* ptr, uint64_t inner, uint64_t outer, uint32_t box_inner, uint32_t box_outer,
                     CUtensorMapSwizzle swz = CU_TENSOR_MAP_SWIZZLE_128B) {
  CUtensorMap m;
  cuuint64_t dims[2] = {inner, outer};
  cuuint64_t strides[1] = {inner * 2};
  cuuint32_t box[2] = {box_inner, box_outer};
  cuuint32_t es[2] = {1, 1};
  enc(&m, CU_TENSOR_MAP_DATA_TYPE_BFLOAT16, 2, const_cast<void*>(ptr), dims, strides, box, es, CU_TENSOR_MAP_INTERLEAVE_NONE,
      swz, CU_TENSOR_MAP_L2_PROMOTION_L2_256B, CU_TENSOR_MAP_FLOAT_OOB_FILL_NONE);
  return m;
}

}

extern "C" void kernel_launch(void* const* d_in, const int* in_sizes, int n_in, void* d_out, int out_size) {
  (void)in_sizes; (void)n_in; (void)out_size;
  static PFN_encode enc = nullptr;
  if (!enc) {
    void* fn = nullptr;
    cudaDriverEntryPointQueryResult qr;
    cudaGetDriverEntryPoint("cuTensorMapEncodeTiled", &fn, cudaEnableDefault, &qr);
    enc = (PFN_encode)fn;
    cudaFuncSetAttribute(mega_kernel, cudaFuncAttributeMaxDynamicSharedMemorySize, SMEM_BYTES);
  }
  Params prm;
  prm.x0 = (const __nv_bfloat16*)d_in[0];
  prm.wA_qkv = (const __nv_bfloat16*)d_in[1];
  prm.wA_o = (const __nv_bfloat16*)d_in[2];
  prm.wB_qkv = (const __nv_bfloat16*)d_in[4];
  prm.wB_phi = (const __nv_bfloat16*)d_in[5];
  prm.wB_o = (const __nv_bfloat16*)d_in[6];
  prm.out = (__nv_bfloat16*)d_out;
  void *obuf = nullptr, *wf = nullptr;
  cudaGetSymbolAddress(&obuf, g_obuf);
  cudaGetSymbolAddress(&wf, g_wfold);
  CUtensorMap tm_x0 = make_map(enc, d_in[0], D_MODEL, S_LEN, 64, 128);
  CUtensorMap tm_xo = make_map(enc, d_out, D_MODEL, S_LEN, 64, 16);
  CUtensorMap tm_os = make_map(enc, obuf, D_MODEL, 2 * S_LEN, 64, 16);
  CUtensorMap tm_o = make_map(enc, obuf, D_MODEL, 2 * S_LEN, 64, 128);
  CUtensorMap tm_wf = make_map(enc, wf, 2048, D_MODEL, 64, 32);
  CUtensorMap tm_wqA = make_map(enc, d_in[1], 3 * D_MODEL, D_MODEL, 64, 32);
  CUtensorMap tm_wqB = make_map(enc, prm.wB_qkv, 3 * D_MODEL, D_MODEL, 64, 32);
  CUtensorMap tm_woA = make_map(enc, prm.wA_o, D_MODEL, D_MODEL, 64, 64);
  CUtensorMap tm_woB = make_map(enc, prm.wB_o, D_MODEL, D_MODEL, 64, 64);
  CUtensorMap tm_phi = make_map(enc, prm.wB_phi, 32, 1024, 32, 128, CU_TENSOR_MAP_SWIZZLE_64B);
  mega_kernel<<<NMAIN + NAUX, 384, SMEM_BYTES>>>(tm_x0, tm_xo, tm_os, tm_o, tm_wf, tm_wqA, tm_wqB, tm_woA, tm_woB, tm_phi, prm);
}
```

```cpp
#include <cuda_runtime.h>
#include <cuda.h>
#include <cuda_bf16.h>
#include <stdint.h>

#define NLAYERS 4

#define STAG1 300
#define HPUMP1 2
#define HPUMP2 2
#define ASKEW 2
#define FPUMP 2
#define PFGAP 100
#define POLLW 4
#define POLL0 0
#define POLLGAP 120
#define BMASK 0x1F
#define ASITE 1
namespace {

constexpr int S_LEN = 2048, D_MODEL = 1024;
constexpr int NAUX = 4, NMAIN = 128;
constexpr int SLOT = 16384;
constexpr int QST = 24576;
constexpr int OFF_RA = 6 * SLOT, OFF_S = 10 * SLOT;
constexpr int OFF_HALO = 13 * SLOT, OFF_LNB = OFF_HALO  , OFF_ONES = OFF_HALO + 3072;
constexpr int OFF_ST = OFF_HALO + 7168  , OFF_PHI = OFF_HALO + 8192;
constexpr int OFF_BAR = 14 * SLOT;
constexpr int OFF_LNA = OFF_BAR + 1024;
constexpr int SMEM_BYTES = OFF_LNA + 2048;
#define WO_ASLOT(par) ((par) ? 0x689C7BA3689C768Cull : 0x68C97BA368C9768Cull)
constexpr unsigned long long WO_BSLOT = 0x5432105421054210ull;
__device__ __forceinline__ int kslice(int j, int i) { return i < 2 ? 2 * j + i : (i < 9 ? 2 * ((j + i - 1) & 7) : 2 * ((j + i) & 7) + 1); }
__device__ __forceinline__ int wslice(int j, int s) { return 2 * ((j + s) & 7) + (s >> 3); }
constexpr int KVH = 5 * 128 * 4;

struct __align__(128) Flag { unsigned v; unsigned pad[31]; };
struct Flags {
  Flag xready[4][16];
  Flag oready[4][16];
  Flag kvready[4][8][16];
  Flag wfready[8];
  Flag done;
  Flag epoch;
};

__device__ Flags g_flags;
__device__ __nv_bfloat16 g_obuf[2 * S_LEN * D_MODEL];
#define O_BIT(l) ((epoch * NLAYERS + (l) + 1) & 1u)
#define X_BIT(l) ((epoch * (NLAYERS - 1) + (l) + 1) & 1u)
__device__ __nv_bfloat16 g_wfold[D_MODEL * 2048];
__device__ uint4 g_halo[16 * 8 * 512];
__device__ float g_kv[2][32 * KVH];
__device__ __align__(128) uint2 g_colsum[2][1536][2];
__device__ __align__(128) uint2 g_stats[S_LEN * 8];
#define STAT_TAG(l) ((ep1 * NLAYERS + (l) + 1) & 3u)

#define RETRY_COUNT()
#define PROFL 1
#define PROFW 0
#define KVFLAG 1
#define PROFT(i) do {} while (0)
#define PROF(i) do {} while (0)

__device__ __forceinline__ uint32_t smem_u32(const void* p) { return (uint32_t)__cvta_generic_to_shared(p); }
__device__ __forceinline__ bool elect_one() {
  uint32_t p;
  asm volatile("{\n.reg .pred p;\nelect.sync _|p, 0xffffffff;\nselp.u32 %0, 1, 0, p;\n}\n" : "=r"(p));
  return p != 0;
}
__device__ __forceinline__ void mbar_init(uint32_t bar, uint32_t cnt) {
  asm volatile("mbarrier.init.shared::cta.b64 [%0], %1;" :: "r"(bar), "r"(cnt));
}
__device__ __forceinline__ void mbar_expect_tx(uint32_t bar, uint32_t bytes) {
  asm volatile("mbarrier.arrive.expect_tx.shared::cta.b64 _, [%0], %1;" :: "r"(bar), "r"(bytes) : "memory");
}
#define mbar_wait(bar, parity) \
  asm volatile("{\n.reg .pred p, q;\nW_%=:\nmbarrier.try_wait.parity.shared::cta.b64 p, [%1], %2;\nadd.s32 %0, %0, -1;\n" \
               "setp.gt.and.s32 q, %0, 0, !p;\n@q bra.uni W_%=;\n}\n" : "+r"(budget) : "r"((uint32_t)(bar)), "r"((uint32_t)(parity)) : "memory")
#define mbar_wait_sl(bar, parity) \
  asm volatile("{\n.reg .pred p, q;\nW_%=:\nmbarrier.try_wait.parity.shared::cta.b64 p, [%1], %2, 20000;\nadd.s32 %0, %0, -64;\n" \
               "setp.gt.and.s32 q, %0, 0, !p;\n@q bra.uni W_%=;\n}\n" : "+r"(budget) : "r"((uint32_t)(bar)), "r"((uint32_t)(parity)) : "memory")
__device__ __forceinline__ void mbar_arrive_local(uint32_t bar) {
  asm volatile("mbarrier.arrive.shared::cta.b64 _, [%0];" :: "r"(bar) : "memory");
}
__device__ __forceinline__ void tma_load_2d(uint32_t dst, const CUtensorMap* tm, uint32_t bar, int c0, int c1) {
  asm volatile("cp.async.bulk.tensor.2d.shared::cluster.global.mbarrier::complete_tx::bytes [%0], [%1, {%3, %4}], [%2];"
               :: "r"(dst), "l"(tm), "r"(bar), "r"(c0), "r"(c1) : "memory");
}
__device__ __forceinline__ void tma_load_2d_mc(uint32_t dst, const CUtensorMap* tm, uint32_t bar, int c0, int c1) {
  asm volatile("cp.async.bulk.tensor.2d.shared::cluster.global.mbarrier::complete_tx::bytes.multicast::cluster [%0], [%1, {%3, %4}], [%2], %5;"
               :: "r"(dst), "l"(tm), "r"(bar), "r"(c0), "r"(c1), "h"((uint16_t)3) : "memory");
}
__device__ __forceinline__ void tma_store_2d(const CUtensorMap* tm, uint32_t src, int c0, int c1) {
  asm volatile("cp.async.bulk.tensor.2d.global.shared::cta.bulk_group [%0, {%2, %3}], [%1];"
               :: "l"(tm), "r"(src), "r"(c0), "r"(c1) : "memory");
}
__device__ __forceinline__ void bulk_commit_wait() {
  asm volatile("cp.async.bulk.commit_group;\ncp.async.bulk.wait_group 0;" ::: "memory");
}
__device__ __forceinline__ void prefetch_tmap(const CUtensorMap* tm) {
  asm volatile("prefetch.tensormap [%0];" :: "l"(tm) : "memory");
}
__device__ __forceinline__ void fence_proxy_async_global() { asm volatile("fence.proxy.async.global;" ::: "memory"); }
__device__ __forceinline__ void fence_proxy_async_smem() { asm volatile("fence.proxy.async.shared::cta;" ::: "memory"); }
__device__ __forceinline__ unsigned ld_relaxed(const unsigned* p) {
  unsigned v;
  asm volatile("ld.relaxed.gpu.global.u32 %0, [%1];" : "=r"(v) : "l"(p) : "memory");
  return v;
}
__device__ __forceinline__ void fence_acquire() { asm volatile("fence.acquire.gpu;" ::: "memory"); }
__device__ __forceinline__ void wait_flag(const unsigned* p, unsigned target) {
  int it = 0;
  while ((int)(ld_relaxed(p) - target) < 0 && ++it < (1 << 20)) {}
  fence_acquire();
}
__device__ __forceinline__ void signal_release(unsigned* p) {
  asm volatile("red.release.gpu.global.add.u32 [%0], 1;" :: "l"(p) : "memory");
}
template <int ID, int N> __device__ __forceinline__ void bar_arrive() { asm volatile("bar.arrive %0, %1;" :: "n"(ID), "n"(N) : "memory"); }
template <int ID, int N> __device__ __forceinline__ void bar_sync() { asm volatile("bar.sync %0, %1;" :: "n"(ID), "n"(N) : "memory"); }
__device__ __forceinline__ void bar_wg(int wg) { asm volatile("bar.sync %0, 128;" :: "r"(2 + wg) : "memory"); }
__device__ __forceinline__ void cluster_sync() {
  asm volatile("barrier.cluster.arrive.relaxed.aligned;\nbarrier.cluster.wait.aligned;" ::: "memory");
}
__device__ __forceinline__ void cluster_wait() { asm volatile("barrier.cluster.wait.acquire.aligned;" ::: "memory"); }
enum { BAR_KV = 4  , BAR_O = 7  , BAR_WF = 12  , BAR_SKEW = 13 };

__device__ __forceinline__ void wgmma_fence() { asm volatile("wgmma.fence.sync.aligned;" ::: "memory"); }
__device__ __forceinline__ void wgmma_commit() { asm volatile("wgmma.commit_group.sync.aligned;" ::: "memory"); }
template <int N> __device__ __forceinline__ void wgmma_wait() { asm volatile("wgmma.wait_group.sync.aligned %0;" :: "n"(N) : "memory"); }

template <int scale_d, int tnsp_b = 1> __device__ __forceinline__ void wgmma_n192(float* d, uint64_t descA, uint64_t descB) {
  asm volatile("{\n.reg .pred p;\nsetp.ne.b32 p, %98, 0;\n"
               "wgmma.mma_async.sync.aligned.m64n192k16.f32.bf16.bf16 {%0,%1,%2,%3,%4,%5,%6,%7,%8,%9,%10,%11,%12,%13,%14,%15,%16,%17,%18,%19,%20,%21,%22,%23,%24,%25,%26,%27,%28,%29,%30,%31,%32,%33,%34,%35,%36,%37,%38,%39,%40,%41,%42,%43,%44,%45,%46,%47,%48,%49,%50,%51,%52,%53,%54,%55,%56,%57,%58,%59,%60,%61,%62,%63,%64,%65,%66,%67,%68,%69,%70,%71,%72,%73,%74,%75,%76,%77,%78,%79,%80,%81,%82,%83,%84,%85,%86,%87,%88,%89,%90,%91,%92,%93,%94,%95}, %96, %97, p, 1, 1, 0, %99;\n}\n"
               : "+f"(d[0]), "+f"(d[1]), "+f"(d[2]), "+f"(d[3]), "+f"(d[4]), "+f"(d[5]), "+f"(d[6]), "+f"(d[7]), "+f"(d[8]), "+f"(d[9]), "+f"(d[10]), "+f"(d[11]), "+f"(d[12]), "+f"(d[13]), "+f"(d[14]), "+f"(d[15]), "+f"(d[16]), "+f"(d[17]), "+f"(d[18]), "+f"(d[19]), "+f"(d[20]), "+f"(d[21]), "+f"(d[22]), "+f"(d[23]), "+f"(d[24]), "+f"(d[25]), "+f"(d[26]), "+f"(d[27]), "+f"(d[28]), "+f"(d[29]), "+f"(d[30]), "+f"(d[31]), "+f"(d[32]), "+f"(d[33]), "+f"(d[34]), "+f"(d[35]), "+f"(d[36]), "+f"(d[37]), "+f"(d[38]), "+f"(d[39]), "+f"(d[40]), "+f"(d[41]), "+f"(d[42]), "+f"(d[43]), "+f"(d[44]), "+f"(d[45]), "+f"(d[46]), "+f"(d[47]), "+f"(d[48]), "+f"(d[49]), "+f"(d[50]), "+f"(d[51]), "+f"(d[52]), "+f"(d[53]), "+f"(d[54]), "+f"(d[55]), "+f"(d[56]), "+f"(d[57]), "+f"(d[58]), "+f"(d[59]), "+f"(d[60]), "+f"(d[61]), "+f"(d[62]), "+f"(d[63]), "+f"(d[64]), "+f"(d[65]), "+f"(d[66]), "+f"(d[67]), "+f"(d[68]), "+f"(d[69]), "+f"(d[70]), "+f"(d[71]), "+f"(d[72]), "+f"(d[73]), "+f"(d[74]), "+f"(d[75]), "+f"(d[76]), "+f"(d[77]), "+f"(d[78]), "+f"(d[79]), "+f"(d[80]), "+f"(d[81]), "+f"(d[82]), "+f"(d[83]), "+f"(d[84]), "+f"(d[85]), "+f"(d[86]), "+f"(d[87]), "+f"(d[88]), "+f"(d[89]), "+f"(d[90]), "+f"(d[91]), "+f"(d[92]), "+f"(d[93]), "+f"(d[94]), "+f"(d[95])
               : "l"(descA), "l"(descB), "n"(scale_d), "n"(tnsp_b));
}
template <int scale_d> __device__ __forceinline__ void wgmma4_n192(float* d, uint32_t da, uint32_t db) {
#define R_ "{%0,%1,%2,%3,%4,%5,%6,%7,%8,%9,%10,%11,%12,%13,%14,%15,%16,%17,%18,%19,%20,%21,%22,%23,%24,%25,%26,%27,%28,%29,%30,%31,%32,%33,%34,%35,%36,%37,%38,%39,%40,%41,%42,%43,%44,%45,%46,%47,%48,%49,%50,%51,%52,%53,%54,%55,%56,%57,%58,%59,%60,%61,%62,%63,%64,%65,%66,%67,%68,%69,%70,%71,%72,%73,%74,%75,%76,%77,%78,%79,%80,%81,%82,%83,%84,%85,%86,%87,%88,%89,%90,%91,%92,%93,%94,%95}"
  asm volatile("{\n.reg .pred p, q;\n.reg .b64 a, b;\nsetp.ne.b32 p, %98, 0;\nsetp.eq.b32 q, 0, 0;\nmov.b64 a, {%96, 0x40000040};\nmov.b64 b, {%97, 0x40000040};\n"
               "wgmma.mma_async.sync.aligned.m64n192k16.f32.bf16.bf16 " R_ ", a, b, p, 1, 1, 0, 1;\nadd.s64 a, a, 2;\nadd.s64 b, b, 128;\n"
               "wgmma.mma_async.sync.aligned.m64n192k16.f32.bf16.bf16 " R_ ", a, b, q, 1, 1, 0, 1;\nadd.s64 a, a, 2;\nadd.s64 b, b, 128;\n"
               "wgmma.mma_async.sync.aligned.m64n192k16.f32.bf16.bf16 " R_ ", a, b, q, 1, 1, 0, 1;\nadd.s64 a, a, 2;\nadd.s64 b, b, 128;\n"
               "wgmma.mma_async.sync.aligned.m64n192k16.f32.bf16.bf16 " R_ ", a, b, q, 1, 1, 0, 1;\n}\n"
               : "+f"(d[0]), "+f"(d[1]), "+f"(d[2]), "+f"(d[3]), "+f"(d[4]), "+f"(d[5]), "+f"(d[6]), "+f"(d[7]), "+f"(d[8]), "+f"(d[9]), "+f"(d[10]), "+f"(d[11]), "+f"(d[12]), "+f"(d[13]), "+f"(d[14]), "+f"(d[15]), "+f"(d[16]), "+f"(d[17]), "+f"(d[18]), "+f"(d[19]), "+f"(d[20]), "+f"(d[21]), "+f"(d[22]), "+f"(d[23]), "+f"(d[24]), "+f"(d[25]), "+f"(d[26]), "+f"(d[27]), "+f"(d[28]), "+f"(d[29]), "+f"(d[30]), "+f"(d[31]), "+f"(d[32]), "+f"(d[33]), "+f"(d[34]), "+f"(d[35]), "+f"(d[36]), "+f"(d[37]), "+f"(d[38]), "+f"(d[39]), "+f"(d[40]), "+f"(d[41]), "+f"(d[42]), "+f"(d[43]), "+f"(d[44]), "+f"(d[45]), "+f"(d[46]), "+f"(d[47]), "+f"(d[48]), "+f"(d[49]), "+f"(d[50]), "+f"(d[51]), "+f"(d[52]), "+f"(d[53]), "+f"(d[54]), "+f"(d[55]), "+f"(d[56]), "+f"(d[57]), "+f"(d[58]), "+f"(d[59]), "+f"(d[60]), "+f"(d[61]), "+f"(d[62]), "+f"(d[63]), "+f"(d[64]), "+f"(d[65]), "+f"(d[66]), "+f"(d[67]), "+f"(d[68]), "+f"(d[69]), "+f"(d[70]), "+f"(d[71]), "+f"(d[72]), "+f"(d[73]), "+f"(d[74]), "+f"(d[75]), "+f"(d[76]), "+f"(d[77]), "+f"(d[78]), "+f"(d[79]), "+f"(d[80]), "+f"(d[81]), "+f"(d[82]), "+f"(d[83]), "+f"(d[84]), "+f"(d[85]), "+f"(d[86]), "+f"(d[87]), "+f"(d[88]), "+f"(d[89]), "+f"(d[90]), "+f"(d[91]), "+f"(d[92]), "+f"(d[93]), "+f"(d[94]), "+f"(d[95])
               : "r"(da), "r"(db), "n"(scale_d));
#undef R_
}
template <int scale_d> __device__ __forceinline__ void wgmma4_n128(float* d, uint32_t da, uint32_t db) {
#define R_ "{%0,%1,%2,%3,%4,%5,%6,%7,%8,%9,%10,%11,%12,%13,%14,%15,%16,%17,%18,%19,%20,%21,%22,%23,%24,%25,%26,%27,%28,%29,%30,%31,%32,%33,%34,%35,%36,%37,%38,%39,%40,%41,%42,%43,%44,%45,%46,%47,%48,%49,%50,%51,%52,%53,%54,%55,%56,%57,%58,%59,%60,%61,%62,%63}"
  asm volatile("{\n.reg .pred p, q;\n.reg .b64 a, b;\nsetp.ne.b32 p, %66, 0;\nsetp.eq.b32 q, 0, 0;\nmov.b64 a, {%64, 0x40000040};\nmov.b64 b, {%65, 0x40000040};\n"
               "wgmma.mma_async.sync.aligned.m64n128k16.f32.bf16.bf16 " R_ ", a, b, p, 1, 1, 0, 1;\nadd.s64 a, a, 2;\nadd.s64 b, b, 128;\n"
               "wgmma.mma_async.sync.aligned.m64n128k16.f32.bf16.bf16 " R_ ", a, b, q, 1, 1, 0, 1;\nadd.s64 a, a, 2;\nadd.s64 b, b, 128;\n"
               "wgmma.mma_async.sync.aligned.m64n128k16.f32.bf16.bf16 " R_ ", a, b, q, 1, 1, 0, 1;\nadd.s64 a, a, 2;\nadd.s64 b, b, 128;\n"
               "wgmma.mma_async.sync.aligned.m64n128k16.f32.bf16.bf16 " R_ ", a, b, q, 1, 1, 0, 1;\n}\n"
               : "+f"(d[0]), "+f"(d[1]), "+f"(d[2]), "+f"(d[3]), "+f"(d[4]), "+f"(d[5]), "+f"(d[6]), "+f"(d[7]), "+f"(d[8]), "+f"(d[9]), "+f"(d[10]), "+f"(d[11]), "+f"(d[12]), "+f"(d[13]), "+f"(d[14]), "+f"(d[15]), "+f"(d[16]), "+f"(d[17]), "+f"(d[18]), "+f"(d[19]), "+f"(d[20]), "+f"(d[21]), "+f"(d[22]), "+f"(d[23]), "+f"(d[24]), "+f"(d[25]), "+f"(d[26]), "+f"(d[27]), "+f"(d[28]), "+f"(d[29]), "+f"(d[30]), "+f"(d[31]), "+f"(d[32]), "+f"(d[33]), "+f"(d[34]), "+f"(d[35]), "+f"(d[36]), "+f"(d[37]), "+f"(d[38]), "+f"(d[39]), "+f"(d[40]), "+f"(d[41]), "+f"(d[42]), "+f"(d[43]), "+f"(d[44]), "+f"(d[45]), "+f"(d[46]), "+f"(d[47]), "+f"(d[48]), "+f"(d[49]), "+f"(d[50]), "+f"(d[51]), "+f"(d[52]), "+f"(d[53]), "+f"(d[54]), "+f"(d[55]), "+f"(d[56]), "+f"(d[57]), "+f"(d[58]), "+f"(d[59]), "+f"(d[60]), "+f"(d[61]), "+f"(d[62]), "+f"(d[63])
               : "r"(da), "r"(db), "n"(scale_d));
#undef R_
}
template <int scale_d> __device__ __forceinline__ void wgmma_n32(float* d, uint64_t descA, uint64_t descB) {
  asm volatile("{\n.reg .pred p;\nsetp.ne.b32 p, %18, 0;\n"
               "wgmma.mma_async.sync.aligned.m64n32k16.f32.bf16.bf16 {%0,%1,%2,%3,%4,%5,%6,%7,%8,%9,%10,%11,%12,%13,%14,%15}, %16, %17, p, 1, 1, 0, 1;\n}\n"
               : "+f"(d[0]), "+f"(d[1]), "+f"(d[2]), "+f"(d[3]), "+f"(d[4]), "+f"(d[5]), "+f"(d[6]), "+f"(d[7]), "+f"(d[8]), "+f"(d[9]), "+f"(d[10]), "+f"(d[11]), "+f"(d[12]), "+f"(d[13]), "+f"(d[14]), "+f"(d[15])
               : "l"(descA), "l"(descB), "n"(scale_d));
}
template <int scale_d, int tnsp_a> __device__ __forceinline__ void wgmma_n40(float* d, uint64_t descA, uint64_t descB) {
  asm volatile("{\n.reg .pred p;\nsetp.ne.b32 p, %22, 0;\n"
               "wgmma.mma_async.sync.aligned.m64n40k16.f32.bf16.bf16 {%0,%1,%2,%3,%4,%5,%6,%7,%8,%9,%10,%11,%12,%13,%14,%15,%16,%17,%18,%19}, %20, %21, p, 1, 1, %23, 1;\n}\n"
               : "+f"(d[0]), "+f"(d[1]), "+f"(d[2]), "+f"(d[3]), "+f"(d[4]), "+f"(d[5]), "+f"(d[6]), "+f"(d[7]), "+f"(d[8]), "+f"(d[9]), "+f"(d[10]), "+f"(d[11]), "+f"(d[12]), "+f"(d[13]), "+f"(d[14]), "+f"(d[15]), "+f"(d[16]), "+f"(d[17]), "+f"(d[18]), "+f"(d[19])
               : "l"(descA), "l"(descB), "n"(scale_d), "n"(tnsp_a));
}
__device__ __forceinline__ uint64_t make_desc(uint32_t addr, uint32_t lbo_bytes, uint32_t sbo_bytes) {
  return (uint64_t)((addr & 0x3FFFF) >> 4) | ((uint64_t)(lbo_bytes >> 4) << 16) | ((uint64_t)(sbo_bytes >> 4) << 32) | (1ull << 62);
}

__device__ __forceinline__ void ldsm_x4(uint32_t addr, uint32_t& r0, uint32_t& r1, uint32_t& r2, uint32_t& r3) {
  asm volatile("ldmatrix.sync.aligned.m8n8.x4.shared.b16 {%0,%1,%2,%3}, [%4];" : "=r"(r0), "=r"(r1), "=r"(r2), "=r"(r3) : "r"(addr) : "memory");
}
__device__ __forceinline__ void ldsm_x4_t(uint32_t addr, uint32_t& r0, uint32_t& r1, uint32_t& r2, uint32_t& r3) {
  asm volatile("ldmatrix.sync.aligned.m8n8.x4.trans.shared.b16 {%0,%1,%2,%3}, [%4];" : "=r"(r0), "=r"(r1), "=r"(r2), "=r"(r3) : "r"(addr) : "memory");
}
__device__ __forceinline__ void stsm_x4(uint32_t addr, uint32_t r0, uint32_t r1, uint32_t r2, uint32_t r3) {
  asm volatile("stmatrix.sync.aligned.m8n8.x4.shared.b16 [%0], {%1,%2,%3,%4};" :: "r"(addr), "r"(r0), "r"(r1), "r"(r2), "r"(r3) : "memory");
}
__device__ __forceinline__ void sts128(uint32_t addr, uint32_t a, uint32_t b, uint32_t c, uint32_t d) {
  asm volatile("st.shared.v4.u32 [%0], {%1,%2,%3,%4};" :: "r"(addr), "r"(a), "r"(b), "r"(c), "r"(d) : "memory");
}
__device__ __forceinline__ float lds32f(uint32_t addr) {
  float v;
  asm volatile("ld.shared.f32 %0, [%1];" : "=f"(v) : "r"(addr) : "memory");
  return v;
}
__device__ __forceinline__ void sts32f(uint32_t addr, float a) {
  asm volatile("st.shared.f32 [%0], %1;" :: "r"(addr), "f"(a) : "memory");
}
__device__ __forceinline__ void mma_bf16(float (&c)[4], uint32_t a0, uint32_t a1, uint32_t a2, uint32_t a3, uint32_t b0, uint32_t b1) {
  asm volatile("mma.sync.aligned.m16n8k16.row.col.f32.bf16.bf16.f32 {%0,%1,%2,%3}, {%4,%5,%6,%7}, {%8,%9}, {%0,%1,%2,%3};"
               : "+f"(c[0]), "+f"(c[1]), "+f"(c[2]), "+f"(c[3]) : "r"(a0), "r"(a1), "r"(a2), "r"(a3), "r"(b0), "r"(b1));
}
__device__ __forceinline__ uint32_t pack_bf16(float lo, float hi) {
  uint32_t r;
  asm("cvt.rn.bf16x2.f32 %0, %1, %2;" : "=r"(r) : "f"(hi), "f"(lo));
  return r;
}
__device__ __forceinline__ float bf_lo(uint32_t v) { return __uint_as_float(v << 16); }
__device__ __forceinline__ float bf_hi(uint32_t v) { return __uint_as_float(v & 0xFFFF0000u); }
__device__ __forceinline__ void split3(float x, uint32_t& h, uint32_t& m, uint32_t& l) {
  h = pack_bf16(x, 0.f); x -= bf_lo(h);
  m = pack_bf16(x, 0.f); x -= bf_lo(m);
  l = pack_bf16(x, 0.f);
}
__device__ __forceinline__ float ex2(float x) { float r; asm("ex2.approx.ftz.f32 %0, %1;" : "=f"(r) : "f"(x)); return r; }
__device__ __forceinline__ float rcp_fast(float x) { float r; asm("rcp.approx.ftz.f32 %0, %1;" : "=f"(r) : "f"(x)); return r; }
__device__ __forceinline__ void red_v4(float* p, float a, float b, float c, float d) {
  asm volatile("red.global.add.v4.f32 [%0], {%1, %2, %3, %4};" :: "l"(p), "f"(a), "f"(b), "f"(c), "f"(d) : "memory");
}
__device__ __forceinline__ uint4 ld_ll(const uint4* p) {
  uint4 v;
  asm volatile("{\n.reg .b64 a, b;\nld.relaxed.gpu.global.v2.b64 {a, b}, [%4];\nmov.b64 {%0, %1}, a;\nmov.b64 {%2, %3}, b;\n}\n"
               : "=r"(v.x), "=r"(v.y), "=r"(v.z), "=r"(v.w) : "l"(p) : "memory");
  return v;
}
__device__ __forceinline__ void st_b64(uint2* p, uint32_t a, uint32_t b) {
  asm volatile("{\n.reg .b64 v;\nmov.b64 v, {%1, %2};\nst.relaxed.gpu.global.b64 [%0], v;\n}\n" :: "l"(p), "r"(a), "r"(b) : "memory");
}
__device__ __forceinline__ void st_b128(uint4* p, uint32_t a, uint32_t b, uint32_t c, uint32_t d) {
  asm volatile("{\n.reg .b128 v;\nmov.b128 v, {%1, %2, %3, %4};\nst.relaxed.gpu.global.b128 [%0], v;\n}\n" :: "l"(p), "r"(a), "r"(b), "r"(c), "r"(d) : "memory");
}
__device__ __forceinline__ uint4 ld_b128(const uint4* p) {
  uint4 v;
  asm volatile("{\n.reg .b128 v;\nld.relaxed.gpu.global.b128 v, [%4];\nmov.b128 {%0, %1, %2, %3}, v;\n}\n" : "=r"(v.x), "=r"(v.y), "=r"(v.z), "=r"(v.w) : "l"(p) : "memory");
  return v;
}

constexpr float LOG2E = 1.4426950408889634f;

struct Params {
  const __nv_bfloat16* x0;
  const __nv_bfloat16* wA_qkv;
  const __nv_bfloat16* wA_o;
  const __nv_bfloat16* wB_qkv;
  const __nv_bfloat16* wB_phi;
  const __nv_bfloat16* wB_o;
  __nv_bfloat16* out;
};

#define ACC_DEF(d, n) _Pragma("unroll") for (int i_ = 0; i_ < (n); i_++) asm volatile("" : "=f"(d[i_]))
#define ACC_FENCE(d, n) _Pragma("unroll") for (int i_ = 0; i_ < (n); i_++) asm volatile("" : "+f"(d[i_]) :: "memory")
#define PIN(a, n) _Pragma("unroll") for (int i_ = 0; i_ < (n); i_++) asm volatile("" : "+f"((a)[i_]))
#define PINU(a, n) _Pragma("unroll") for (int i_ = 0; i_ < (n); i_++) asm volatile("" : "+r"((a)[i_]))

#define STAGE64(acc, off, p0, KIND, SEND) { \
    uint32_t w_[4][4]; \
    _Pragma("unroll") for (int j_ = 0; j_ < 4; j_++) { \
      const int o_ = (off) + j_ * 8; \
      w_[j_][0] = pack_bf16(rs0 * acc[o_ + 0], rs0 * acc[o_ + 1]); \
      w_[j_][1] = pack_bf16(rs1 * acc[o_ + 2], rs1 * acc[o_ + 3]); \
      w_[j_][2] = pack_bf16(rs0 * acc[o_ + 4], rs0 * acc[o_ + 5]); \
      w_[j_][3] = pack_bf16(rs1 * acc[o_ + 6], rs1 * acc[o_ + 7]); \
    } \
    if ((SEND) && hsend) { \
      _Pragma("unroll") for (int j_ = 0; j_ < 4; j_++) { \
        w_[j_][0] = (w_[j_][0] & ~1u) | hbit; \
        st_b128(hbase + lane + ((KIND) * 4 + j_) * 32, w_[j_][0], w_[j_][1], w_[j_][2], w_[j_][3]); \
      } \
    } \
    _Pragma("unroll") for (int j_ = 0; j_ < 4; j_++) \
      stsm_x4((KIND) ? (p0) + (j_ >> 1) * 8192 + (srowoff >> 1) + ((((uint32_t)(j_ & 1) << 5) + lhi) ^ lsw2) \
                     : (p0) + srowoff + ((((uint32_t)j_ << 5) + lhi) ^ lsw), \
              w_[j_][0], w_[j_][1], w_[j_][2], w_[j_][3]); \
  }
#define RW(j) (((j) >> 1) * 4 + ((j) & 1))
__device__ __forceinline__ float rmax16(const float* p) {
  float m[4];
#pragma unroll
  for (int j = 0; j < 4; j++) m[j] = fmaxf(fmaxf(p[RW(j)], p[RW(j + 4)]), fmaxf(p[RW(j + 8)], p[RW(j + 12)]));
  const float r = fmaxf(fmaxf(m[0], m[1]), fmaxf(m[2], m[3]));
  return fmaxf(r, __shfl_xor_sync(0xffffffffu, r, 1));
}
__device__ __forceinline__ float rmin16(const float* p) {
  float m[4];
#pragma unroll
  for (int j = 0; j < 4; j++) m[j] = fminf(fminf(p[RW(j)], p[RW(j + 4)]), fminf(p[RW(j + 8)], p[RW(j + 12)]));
  const float r = fminf(fminf(m[0], m[1]), fminf(m[2], m[3]));
  return fminf(r, __shfl_xor_sync(0xffffffffu, r, 1));
}
__device__ __forceinline__ float exps16(float* o, const float* p, float c, float b) {
  float s[4];
#pragma unroll
  for (int j = 0; j < 16; j++) { o[j] = ex2(fmaf(p[RW(j)], c, b)); if (j < 4) s[j] = o[j]; else s[j & 3] += o[j]; }
  return (s[0] + s[1]) + (s[2] + s[3]);
}
__device__ __forceinline__ void store16(const float* e, float sum, uint32_t dst, uint32_t dsw, int c0) {
  const float inv = rcp_fast(sum + __shfl_xor_sync(0xffffffffu, sum, 1));
#pragma unroll
  for (int j = 0; j < 2; j++)
    sts128(dst + (((c0 + j) << 4) ^ dsw), pack_bf16(e[j * 8] * inv, e[j * 8 + 1] * inv), pack_bf16(e[j * 8 + 2] * inv, e[j * 8 + 3] * inv),
           pack_bf16(e[j * 8 + 4] * inv, e[j * 8 + 5] * inv), pack_bf16(e[j * 8 + 6] * inv, e[j * 8 + 7] * inv));
}
__device__ __forceinline__ void expp16(uint32_t* o, const float* p, float c, float b) {
#pragma unroll
  for (int j = 0; j < 8; j++) o[j] = pack_bf16(ex2(fmaf(p[4 * j], c, b)), ex2(fmaf(p[4 * j + 1], c, b)));
}
#define SCHED_FENCE() asm volatile("pmevent 0;" ::: "memory")

__global__ void __cluster_dims__(2, 1, 1) __launch_bounds__(384, 1)
mega_kernel(const __grid_constant__ CUtensorMap tm_x0, const __grid_constant__ CUtensorMap tm_xo, const __grid_constant__ CUtensorMap tm_os,
            const __grid_constant__ CUtensorMap tm_o, const __grid_constant__ CUtensorMap tm_wf,
            const __grid_constant__ CUtensorMap tm_wqA, const __grid_constant__ CUtensorMap tm_wqB,
            const __grid_constant__ CUtensorMap tm_woA, const __grid_constant__ CUtensorMap tm_woB,
            const __grid_constant__ CUtensorMap tm_phi, const Params prm) {
  extern __shared__ __align__(1024) uint8_t smem_raw[];
  const uint32_t sbase = smem_u32(smem_raw);
  const uint32_t bar_full = sbase + OFF_BAR;
  const uint32_t bar_done = bar_full + 384;
  const uint32_t bar_stat = bar_full + 768, bar_stat2 = bar_full + 776, bar_epi = bar_full + 784, bar_phi = bar_full + 936  ;
  const uint32_t bar_xr = bar_full + 800, bar_lx = bar_full + 808, bar_kvf = bar_full + 816  , bar_stg = bar_full + 832;
  const uint32_t bar_chk = bar_full + 848;

  const int warp = __shfl_sync(0xffffffffu, threadIdx.x >> 5, 0), lane = threadIdx.x & 31;
  uint32_t rank;
  asm volatile("mov.u32 %0, %%cluster_ctarank;" : "=r"(rank));
  const int cta = (int)blockIdx.x - NAUX;
  const int cl = cta >> 1;
  const int jj = cl & 7, cc = cl >> 3;
  const int mm = cc * 2 + (int)rank;

#define LOAD_EPOCH() const unsigned epoch = ld_relaxed(&g_flags.epoch.v), ep1 = epoch + 1; (void)epoch
  int budget = 1 << 22;

  if (cta >= 0) {
    {
      const int tx = threadIdx.x;
      const __nv_bfloat16* pf = (tx < 128) ? prm.x0 + (size_t)(mm * 128 + tx) * D_MODEL + jj * 128
                                           : prm.wA_qkv + (size_t)(jj * 128 + (tx & 63)) * 3072 + ((tx - 128) >> 6) * 1024 + jj * 128 + rank * 64;
      if (tx < 320) asm volatile("prefetch.global.L2 [%0];" :: "l"(pf));
      else if (tx == 320) prefetch_tmap(&tm_x0);
      else if (tx == 352) prefetch_tmap(&tm_wqA);
      else if (tx == 383) asm volatile("prefetch.global.L2 [%0];" :: "l"(&g_flags.epoch.v));
    }
    if (elect_one()) {
#pragma unroll
      for (int i = 0; i < 4; i++) {
        const int u = warp * 4 + i;
        mbar_init(bar_full + u * 8, ((u >= 4 && u < 11) || u > 40) ? 2 : 1); mbar_init(bar_done + u * 8, 16);
      }
      mbar_init(bar_stat + warp * 16, 0x111111181182ull >> (4 * warp) & 15);
      mbar_init(bar_stat + warp * 16 + 8, 0x111111121811ull >> (4 * warp) & 15);
      asm volatile("fence.mbarrier_init.release.cluster;" ::: "memory");
    }
    __syncthreads();
    asm volatile("barrier.cluster.arrive.relaxed.aligned;" ::: "memory");
  }

  if (cta < 0) {
    LOAD_EPOCH();
    const uint32_t buf = sbase + warp * SLOT, bar = sbase + OFF_BAR + warp * 16;
    const uint32_t lsw = (lane & 7) << 4, lhi = (lane >> 4) << 4, lrow = (lane & 15) * 128;
    const bool el = elect_one();
    if (el) {
      mbar_init(bar, 1); mbar_init(bar + 8, 1);
      asm volatile("fence.mbarrier_init.release.cluster;" ::: "memory");
    }
#pragma unroll 1
    for (int rd = 0; rd < (NLAYERS > 1 ? 5 : 2); rd++) {
      if (rd >= 2 && warp >= 8) break;
      const int tk = rd < 2 ? blockIdx.x * 12 + warp : blockIdx.x * 8 + warp;
      const int half = tk & 1;
      const int blk = rd < 2 ? (tk >> 1) * 2 + rd : (4 - rd) * 16 + (tk >> 1);
      const CUtensorMap* tm = rd < 2 ? &tm_wqA : (rd == 2 ? &tm_wqB : &tm_wf);
      const int j0 = (blk & 15) >> 1;
#define AUX_LOAD(n) { const uint32_t d_ = buf + ((n) & 1) * 8192, b_ = bar + ((n) & 1) * 8; const int r_ = kslice(j0, 2 * (n) + half) * 64; \
        mbar_expect_tx(b_, 8192); tma_load_2d(d_, tm, b_, blk * 64, r_); tma_load_2d(d_ + 4096, tm, b_, blk * 64, r_ + 32); }
      if (el) {
        if (rd == 3) { wait_flag(&g_flags.wfready[j0].v, ep1 * 16); fence_proxy_async_global(); }
        AUX_LOAD(0); AUX_LOAD(1);
      }
      __syncwarp();
      float cs[8][4];
#pragma unroll
      for (int i = 0; i < 8; i++) cs[i][0] = cs[i][1] = cs[i][2] = cs[i][3] = 0.f;
#pragma unroll 1
      for (int n = 0; n < 8; n++) {
        const uint32_t tb = buf + (n & 1) * 8192 + lrow;
        mbar_wait(bar + (n & 1) * 8, (n >> 1) & 1);
#pragma unroll
        for (int i = 0; i < 16; i++) {
          uint32_t b0, b1, b2, b3;
          ldsm_x4_t(tb + (i >> 2) * 2048 + (((i & 3) * 32 + lhi) ^ lsw), b0, b1, b2, b3);
          mma_bf16(cs[2 * (i & 3)], 0x3F803F80u, 0x3F803F80u, 0x3F803F80u, 0x3F803F80u, b0, b1);
          mma_bf16(cs[2 * (i & 3) + 1], 0x3F803F80u, 0x3F803F80u, 0x3F803F80u, 0x3F803F80u, b2, b3);
        }
        __syncwarp();
        if (el && n < 6) AUX_LOAD(n + 2);
        __syncwarp();
      }
      if (lane < 4) {
#pragma unroll
        for (int i = 0; i < 8; i++) st_b64(&g_colsum[rd >= 2][blk * 32 + i * 4 + lane][half], __float_as_uint(cs[i][0]), (__float_as_uint(cs[i][1]) & ~3u) | (ep1 & 3));
      }
      __syncwarp();
    }
  } else if (warp >= 8) {
    asm volatile("setmaxnreg.dec.sync.aligned.u32 40;");
    if (warp == 8) {
      const bool el = elect_one();
      cluster_wait();
      if (el) {
#pragma unroll 1
        for (int l = 0; l < NLAYERS; l++) {
          const uint32_t par = l & 1;
          const CUtensorMap* tqk = par ? &tm_wf : &tm_wqA;
          const CUtensorMap* tv = par ? &tm_wqB : &tm_wqA;
          const CUtensorMap* two = par ? &tm_woB : &tm_woA;
          if (l == 1) { LOAD_EPOCH(); wait_flag(&g_flags.wfready[jj].v, ep1 * 16); fence_proxy_async_global(); }
#pragma unroll 1
          for (int u = 0; u < 32; u++) {
            if (u >= 4) mbar_wait_sl(bar_done + (u - 4) * 8, par);
            else if (l) mbar_wait_sl(bar_done + (43 + u + (u >> 1)) * 8, par ^ 1);
            else if (u == 1) __nanosleep(STAG1);
            else if (u == 2) mbar_wait_sl(bar_full, 0);
            const uint32_t fb = bar_full + u * 8;
            const bool res = u < 4 ? (l || u >= 2) : (u < 11 || (u >= 18 && u < 22));
            mbar_expect_tx(fb, res ? QST : QST + SLOT);
            const int row = kslice(jj, u < 4 ? u & 1 : (u < 18 ? u - 2 : (u < 22 ? u - 6 : u - 20))) * 64 + (int)rank * 32;
            const int ps = u < 4 ? u >> 1 : (u >= 18), col = jj * 128 + ps * 64;
            const int c0 = par ? jj * 128 + (ps ? 0 : 1024) : col;
            const uint32_t dst = sbase + (u & 3) * QST + rank * 4096;
            tma_load_2d_mc(dst, tqk, fb, c0, row);
            tma_load_2d_mc(dst + 8192, tqk, fb, c0 + (par ? 64 : 1024), row);
            tma_load_2d_mc(dst + 16384, tv, fb, col + 2048, row);
            if (l == 0 && u < 4) PROFT(473 + u);
          }
#pragma unroll 1
          for (int s = 0; s < 16; s++) {
            if (s < 5) { if (s != 2 && s != 4) mbar_wait_sl(bar_done + (28 + s) * 8, par); }
            else if (s != 14) mbar_wait_sl(bar_done + (27 + s - (s == 15)) * 8, par);
            const uint32_t fb = bar_full + (32 + s) * 8;
            mbar_expect_tx(fb, (s && s < 8) ? 2 * SLOT : SLOT);
            tma_load_2d_mc(sbase + rank * 8192 + (uint32_t)((WO_BSLOT >> (4 * s)) & 15) * SLOT, two, fb, jj * 128 + (int)rank * 64, wslice(jj, s) * 64);
            if (s >= 5 && s < 8) {
              if (s == 5) { mbar_wait_sl(bar_full + 33 * 8, par); fence_proxy_async_global(); mbar_wait_sl(bar_epi, par); }
              tma_load_2d(sbase + (uint32_t)((WO_ASLOT(par) >> (4 * s)) & 15) * SLOT, &tm_o, fb, wslice(jj, s) * 64, mm * 128);
            }
          }
        }
      }
      __syncwarp();
    } else if (warp == 9) {
      const bool el = elect_one();
      if (el) {
        PROFT(472);
        tma_load_2d(sbase + OFF_S, &tm_x0, bar_full, jj * 128, mm * 128);
        __nanosleep(STAG1);
        tma_load_2d(sbase + OFF_S + SLOT, &tm_x0, bar_full + 8, jj * 128 + 64, mm * 128);
      }
      __syncwarp();
      LOAD_EPOCH();
#pragma unroll 1
      for (int lp = 0; lp < 2 * NLAYERS; lp++) {
        const int l = lp >> 1, ph = lp & 1;
        const uint32_t par = l & 1;
        const __nv_bfloat16* pb = g_obuf + ph * 64 + (size_t)(mm * 128 + (ph ? 0 : S_LEN) + (lane & 7) * 16 + (jj & 1) * 8) * D_MODEL + (jj >> 1) * 16;
        const CUtensorMap* tm = lp ? &tm_o : &tm_x0;
        const int row = mm * 128 + ((ph || !l) ? 0 : S_LEN);
        const uint32_t bit = ph ? O_BIT(l) : X_BIT(l - 1);
        const uint32_t slots = ph ? (uint32_t)(WO_ASLOT(par) >> 36) : 0x8769876u;
        uint32_t rdy = lp ? 0 : 0xFF;
        mbar_wait_sl(ph ? bar_epi : (l ? bar_done + 47 * 8 : bar_full), ph ? par : (l ? par ^ 1 : 0));
#pragma unroll 1
        for (int i = 0; i < 7; i++) {
          if (!((rdy >> i) & 1)) {
            const unsigned* pp = reinterpret_cast<const unsigned*>(pb + ((jj + i + 1 + ((lane >> 3) & (POLLW - 1))) & 7) * 128);
            if (i == 0) __nanosleep(POLL0);
            unsigned v0 = ld_relaxed(pp);
            __nanosleep(POLLGAP);
            unsigned v1 = ld_relaxed(pp);
            uint32_t no;
#pragma unroll 1
            for (int it = 0; it < (1 << 18); it++) {
              no = __ballot_sync(0xffffffffu, (v0 ^ bit) & 1);
              if (!(no & 0xFF)) break;
              v0 = ld_relaxed(pp);
              no = __ballot_sync(0xffffffffu, (v1 ^ bit) & 1);
              if (!(no & 0xFF)) break;
              v1 = ld_relaxed(pp);
            }
            rdy = ((1 | (no & 0xFF00 ? 0 : 2) | (no & 0xFF0000 ? 0 : 4) | (no >> 24 ? 0 : 8)) & ((1 << POLLW) - 1)) << i;
          }
          if (i >= (ph ? 2 : 4)) mbar_wait_sl(bar_done + (i + (ph ? 33 : 0)) * 8, par);
          if (el) {
            if (i == 0) PROFT(320 + l * 16 + ph * 2);
            mbar_expect_tx(bar_chk + i * 8, SLOT);
            tma_load_2d(sbase + ((slots >> (4 * i)) & 15) * SLOT, tm, bar_chk + i * 8, ((jj + i + 1) & 7) * 128 + ph * 64, row);
          }
          __syncwarp();
        }
        if (ph == 0 && el) {
          if (l) { wait_flag(&g_flags.xready[l][mm].v, ep1 * 8); fence_proxy_async_global(); }
#pragma unroll 1
          for (int u = 11; u < 34; u++) {
            if (u == 18) u = 22;
            mbar_wait_sl(bar_done + (u - 4) * 8, par);
            if (u == 32) mbar_expect_tx(bar_xr, 2 * SLOT);
            tma_load_2d(sbase + OFF_RA + (u & 3) * SLOT, tm, u < 32 ? bar_full + u * 8 : bar_xr, kslice(jj, u < 18 ? u - 2 : (u < 32 ? u - 20 : u - 32)) * 64, row);
            if (l == 0 && u < 16 && NLAYERS > 1) {
              if (u == 11) { mbar_expect_tx(bar_phi, SLOT + 8192); tma_load_2d(sbase + OFF_PHI, &tm_phi, bar_phi, 0, jj * 128); }
              else tma_load_2d(sbase + 12 * SLOT + (u - 12) * 4096, &tm_wqB, bar_phi, jj * 128 + ((u - 12) >> 1) * 64, mm * 64 + (u & 1) * 32);
            }
          }
          wait_flag(&g_flags.oready[l][mm].v, ep1 * 8);
          fence_proxy_async_global();
          PROFT(321 + l * 16);
#pragma unroll 1
          for (int s = 1; s < 5; s++) {
            if (s != 3) mbar_wait_sl(s == 2 ? bar_lx : bar_done + (s == 1 ? 30 : 31 + par) * 8, par);
            tma_load_2d(sbase + (uint32_t)((WO_ASLOT(par) >> (4 * s)) & 15) * SLOT, &tm_o, bar_full + (32 + s) * 8, wslice(jj, s) * 64, mm * 128);
          }
        }
        __syncwarp();
      }
      cluster_wait();
    } else {
      const int hw = warp - 10;
      LOAD_EPOCH();
      const bool el = elect_one();
      cluster_wait();
      if (hw == 0) {
        mbar_wait_sl(bar_full + 8, 0);
        if (lane < 7) prefetch_tmap(lane == 0 ? &tm_os : lane == 1 ? &tm_o : lane == 2 ? &tm_wf : lane == 3 ? &tm_wqB : lane == 4 ? &tm_woA : lane == 5 ? &tm_woB : &tm_phi);
        if (lane < 4) asm volatile("prefetch.global.L2 [%0];" :: "l"(prm.wB_phi + jj * 4096 + mm * 256 + lane * 64));
#pragma unroll 1
        for (int i = 0; i < 8; i++) {
          asm volatile("prefetch.global.L2 [%0];" :: "l"(prm.wB_qkv + (size_t)(mm * 64 + (i & 3) * 16 + (lane >> 1)) * 3072 + (i >> 2) * 1024 + jj * 128 + (lane & 1) * 64));
          __nanosleep(PFGAP);
        }
      } else {
#pragma unroll 1
        for (int b = 0; b < 2; b++) {
          float4* z = reinterpret_cast<float4*>(g_kv[b] + (jj * 4) * KVH + mm * (4 * KVH / 16)) + lane;
#pragma unroll
          for (int i = 0; i < 5; i++) z[i * 32] = make_float4(0.f, 0.f, 0.f, 0.f);
        }
      }
      __syncwarp();
      uint32_t chkp = 0;
#pragma unroll 1
      for (int lp = 0; lp < 2 * NLAYERS; lp++) {
        const int l = lp >> 1, ph = lp & 1;
        const uint32_t par = l & 1;
        int lane; asm volatile("mov.u32 %0, %%laneid;" : "=r"(lane));
        if (hw) {
          const uint32_t bit = ph ? O_BIT(l) : X_BIT(l - 1);
          const uint32_t slots = ph ? (uint32_t)(WO_ASLOT(par) >> 36) : 0x8769876u;
#pragma unroll 1
          for (int c = 0; c < 7; c++) {
            const uint32_t tile = sbase + ((slots >> (4 * c)) & 15) * SLOT;
#pragma unroll 1
            for (int it = 0; it < (1 << 12); it++) {
              mbar_wait_sl(bar_chk + c * 8, (chkp >> c) & 1);
              chkp ^= 1u << c;
              if (el && c == 0) PROFT(488 + lp);
              if (lp == 0) break;
              uint32_t a1 = 1, o1 = 0;
#pragma unroll
              for (int i = 0; i < 16; i++) {
                uint32_t w;
                asm volatile("ld.shared.u32 %0, [%1];" : "=r"(w) : "r"(tile + i * 1024 + (lane & 7) * 132 + (lane >> 3) * 32) : "memory");
                a1 &= w; o1 |= w;
              }
              if (__all_sync(0xffffffffu, ((bit ? a1 : ~o1) & 1) != 0)) break;
              if (el) {
                fence_proxy_async_smem();
                mbar_expect_tx(bar_chk + c * 8, SLOT);
                tma_load_2d(tile, &tm_o, bar_chk + c * 8, ((jj + c + 1) & 7) * 128 + ph * 64, mm * 128 + (ph ? 0 : S_LEN));
                RETRY_COUNT();
              }
              __syncwarp();
            }
            if (el) mbar_arrive_local(bar_full + (c + (ph ? 41 : 4)) * 8);
            __syncwarp();
          }
          if (ph) continue;
#pragma unroll 1
          for (int hp = 0; hp < 2; hp++) {
            const uint4* src = reinterpret_cast<const uint4*>(g_colsum[par][jj * 64 + hp * 32 + lane]);
            uint32_t bad;
            int it = 0;
            float c[6];
            do {
              bad = 0;
#pragma unroll
              for (int p = 0; p < 3; p++) {
                const uint4 v = ld_ll(src + ((par && p < 2) ? (hp ? -32 : 512) + p * 32 : p * 512));
                bad |= (v.y ^ ep1) | (v.w ^ ep1);
                c[2 * p] = __uint_as_float(v.x) + __uint_as_float(v.z); c[2 * p + 1] = __uint_as_float(v.y) + __uint_as_float(v.w);
              }
              bad &= 3;
              if (bad) __nanosleep(300);
            } while (bad && ++it < (1 << 16));
#pragma unroll
            for (int p = 0; p < 6; p++) {
              uint32_t h, m, lo;
              split3(c[p], h, m, lo);
              sts128(sbase + OFF_LNB + hp * 4096 + (p >> 1) * 1024 + lane * 32 + (p & 1) * 16, h | (m << 16), h | (lo << 16), h | (m << 16), lo | (m << 16));
            }
            fence_proxy_async_smem();
            __syncwarp();
            if (el) { mbar_arrive_local(hp ? bar_stat2 : bar_stat); if (hp == 0) PROFT(324 + l * 16); }
            __syncwarp();
          }
        } else if (ph == 0) {
          mbar_wait_sl(bar_done + 24, par);
          const uint4* sp = reinterpret_cast<const uint4*>(g_stats + (size_t)(mm * 128) * 8) + lane;
#pragma unroll 1
          for (int hf = 0; hf < 4; hf++) {
            uint4 v[4];
            uint32_t bad;
            int it = 0;
            do {
              bad = 0;
#pragma unroll
              for (int i = 0; i < 4; i++) { v[i] = ld_ll(sp + (hf * 4 + i) * 32); bad |= (v[i].y ^ STAT_TAG(l)) | (v[i].w ^ STAT_TAG(l)); }
              bad &= 3;
              if (bad) __nanosleep(200);
            } while (bad && ++it < (1 << 16));
            __syncwarp();
            float mean = 0.f, m2 = 0.f;
#pragma unroll
            for (int i = 0; i < 4; i++) {
              float a = __uint_as_float(v[i].x) + __uint_as_float(v[i].z);
              a += __shfl_xor_sync(0xffffffffu, a, 1); a += __shfl_xor_sync(0xffffffffu, a, 2);
              a *= 0.125f;
              const float e0 = __uint_as_float(v[i].x) - a, e1 = __uint_as_float(v[i].z) - a;
              float q = fmaf(fmaf(e0, e0, e1 * e1), 128.f, __uint_as_float(v[i].y) + __uint_as_float(v[i].w));
              q += __shfl_xor_sync(0xffffffffu, q, 1); q += __shfl_xor_sync(0xffffffffu, q, 2);
              if ((lane & 3) == i) { mean = a; m2 = q; }
            }
            const uint32_t row = hf * 32 + (lane & 3) * 8 + (lane >> 2);
            uint32_t h, m, lo;
            split3(-0.5f * mean, h, m, lo);
            sts128(sbase + OFF_LNA + row * 16, h | (h << 16), m | (h << 16), lo | (m << 16), m | (lo << 16));
            sts32f(sbase + OFF_ST + row * 4, rsqrtf(m2 * (1.f / 1024.f) + 1e-5f));
          }
          fence_proxy_async_smem();
          __syncwarp();
          if (el) { mbar_arrive_local(bar_stat); PROFT(323 + l * 16); }
          __syncwarp();
#pragma unroll 1
          for (int i = 0; i < 8 - 4 * l; i++) {
            asm volatile("prefetch.global.L2 [%0];" :: "l"(i < 4 ? (l ? prm.wB_o : prm.wA_o) + (size_t)cta * 8192 + i * 2048 + lane * 64
                                                                 : prm.wB_qkv + (size_t)(cta * 8 + (i - 4) * 2 + (lane >> 4)) * 3072 + 2048 + (lane & 15) * 64));
            __nanosleep(PFGAP);
          }
          continue;
        }
        if (hw) {
          if (l & 1) {
#pragma unroll 1
            for (int h = 0; h < 2; h++) {
              asm volatile("bar.sync %0, 288;" :: "r"(BAR_KV + h) : "memory");
              __syncwarp();
              PROFT(331 + l * 16 + h);
              if (lane < 16) signal_release(&g_flags.kvready[(l & 2) + h][jj][lane].v);
              const unsigned* kf = &g_flags.kvready[(l & 2) + h][jj][mm].v;
              unsigned v0 = ld_relaxed(kf);
              __nanosleep(150);
              unsigned v1 = ld_relaxed(kf);
#pragma unroll 1
              for (int it = 0; it < (1 << 18); it++) {
                if (v0 == ep1 * 16) break;
                v0 = ld_relaxed(kf);
                if (v1 == ep1 * 16) break;
                v1 = ld_relaxed(kf);
              }
              fence_acquire();
              __syncwarp();
              if (el) { mbar_arrive_local(bar_kvf + h * 8); PROFT(333 + l * 16 + h); }
              __syncwarp();
            }
          }
        } else {
#pragma unroll 1
          for (uint32_t ev = l == NLAYERS - 1 ? 0x80u : (l == 0 ? 0x836054u : 0x830u); ev != 8; ev >>= 4) {
            const int e = ev & 15;
            asm volatile("bar.sync %0, 288;" :: "r"((0xFECA987 >> (4 * e)) & 15) : "memory");
            if (el) {
              if (e < 4) {
                PROFT(325 + l * 16 + e);
                tma_store_2d(&tm_o, sbase + (e ? 11 : 12) * SLOT, jj * 128 + (e & 1) * 64, mm * 128 + (e ? S_LEN : 0));
              } else {
                if (e == 5) mbar_expect_tx(bar_phi + 8, SLOT);
#pragma unroll 1
                for (int i = 0; i < 4; i++) {
                  const uint32_t a = sbase + (e > 4 ? 10 : 12) * SLOT + i * 4096;
                  const int c0 = (e > 4 ? 1024 : 0) + jj * 128 + (i >> 1) * 64, c1 = mm * 64 + (i & 1) * 32;
                  if (e == 5) tma_load_2d(a, &tm_wqB, bar_phi + 8, c0, c1); else tma_store_2d(&tm_wf, a, c0, c1);
                }
                if (e != 5) {
                  asm volatile("cp.async.bulk.commit_group;\ncp.async.bulk.wait_group.read 0;" ::: "memory");
                  mbar_arrive_local(bar_phi + (e - 4) * 4);
                }
              }
              if ((0x49 >> e) & 1) {
                bulk_commit_wait();
                signal_release(e == 0 ? &g_flags.oready[l][mm].v : e == 6 ? &g_flags.wfready[jj].v : &g_flags.xready[l + 1][mm].v);
              }
              if (e == 3) PROFT(330 + l * 16);
              if (e == 6) PROFT(335);
            }
            __syncwarp();
          }
        }
      }
    }
    cluster_sync();
  } else {
    asm volatile("setmaxnreg.inc.sync.aligned.u32 232;");
    LOAD_EPOCH();
    const int wg = warp >> 2;
    const int r0 = warp * 16;
    const uint32_t pK = sbase + OFF_S, pV = sbase + OFF_S + SLOT;
#define PMASKS(on, bit) const uint32_t pm0 = ((on) && t == (g & 3) && (g >> 2) == (g & 1)), pm1 = ((on) && t == (g & 3) && (g >> 2) != (g & 1)), pbit = (bit)
#define PBIT0(w) (((w) & ~pm0) | (pbit & pm0))
#define PBIT1(w) (((w) & ~pm1) | (pbit & pm1))
#define LANE_CONSTS() \
    int lane; asm volatile("mov.u32 %0, %%laneid;" : "=r"(lane)); \
    const int g = lane >> 2, t = lane & 3; \
    const uint32_t srowoff = (r0 + (lane & 15)) * 128, lsw = (lane & 7) << 4, lhi = (lane >> 4) << 4, lsw2 = (lane & 6) << 3; \
    (void)g; (void)t; (void)srowoff; (void)lsw; (void)lhi; (void)lsw2;
    uint32_t stgp = 0, peer;
    asm volatile("mapa.shared::cluster.u32 %0, %1, %2;" : "=r"(peer) : "r"(sbase), "r"(rank ^ 1));
    peer -= sbase;
    const uint32_t dA0 = (((sbase & 0x3FFFF) + wg * 8192) >> 4) | 0x10000u, dB0 = ((sbase & 0x3FFFF) >> 4) | 0x2000000u;
    cluster_wait();
#define STG_ARRIVE() { __syncwarp(); if (elect_one()) mbar_arrive_local(bar_stg); }
#define STG_WAIT() { mbar_wait(bar_stg, stgp); stgp ^= 1; }
#define PROFS() do {} while (0)
#define REL(addr) { if (elect_one()) { mbar_arrive_local(addr); asm volatile("mbarrier.arrive.shared::cluster.b64 _, [%0];" :: "r"((addr) + peer) : "memory"); } }
#define QSTEP(ACC, DA, SC, PRE) { \
      const uint32_t da = (DA), db = dB0 + (ub & 0x18) * (QST >> 7); \
      mbar_wait(ub, par); \
      PRE; \
      wgmma_fence(); \
      wgmma4_n192<SC>(ACC, da, db); \
      wgmma_commit(); PROFS(); }
#define QREL() { wgmma_wait<1>(); REL(ub + 376); ub += 8; }
#define RA_CUR (dA0 + (OFF_RA >> 4) + (ub & 0x18) * (SLOT >> 7))
#define PUMP1() { QSTEP(S1, RA_CUR, 1, {}); QREL(); }
#define PUMP0() { PUMP1(); SCHED_FENCE(); }
#define PUMP() if (h == 0) PUMP1()
#define WSTEP() { \
      const uint32_t s4 = (ub - bar_full - 256) >> 1; \
      const uint32_t da = dA0 + (((uint32_t)(WO_ASLOT(par) >> s4) & 15) << 10), db = dB0 + (((uint32_t)(WO_BSLOT >> s4) & 15) << 10); \
      mbar_wait(ub, par); \
      wgmma_fence(); \
      wgmma4_n128<1>(S1, da, db); \
      wgmma_commit(); PROFS(); \
      wgmma_wait<1>(); \
      if (s4 > par * 4) REL(ub + 376); \
      ub += 8; }
#define PUMPS(n) { _Pragma("unroll 1") for (int i_ = 0; i_ < (n); i_++) PUMP1(); }
#define SITE(n) { if ((BMASK >> (n)) & 1) PUMP1(); SCHED_FENCE(); }
#define LNSTEP(ACC, hh) { wgmma_fence(); wgmma_n192<1, 0>(ACC, make_desc(sbase + OFF_LNA + wg * 1024, 0, 128) ^ (1ull << 62), make_desc(sbase + OFF_LNB + (hh) * 4096, 0, 128) ^ (1ull << 62)); }
#define DRAIN_A(ACC, PMP) { \
      LANE_CONSTS(); \
      STAGE64(ACC, 64, pV, 1, 1); \
      PMP; \
      STAGE64(ACC, 32, pK, 0, 1); \
      STG_ARRIVE(); \
      _Pragma("unroll") for (int i_ = 0; i_ < 16; i_++) qa[i_] = pack_bf16(ACC[2 * i_], ACC[2 * i_ + 1]); \
      PINU(qa, 16); }
#define DRAIN_B(ACC) { \
      LANE_CONSTS(); \
      STAGE64(ACC, 64, pV, 1, 0); \
      _Pragma("unroll") for (int i_ = 0; i_ < 64; i_++) st[i_] = ACC[i_]; \
      PIN(st, 64); }
#define WARP_STORE(tm, tile, col, row) { fence_proxy_async_smem(); __syncwarp(); \
      if (elect_one()) { tma_store_2d(tm, (tile) + r0 * 128, col, (row) + r0); asm volatile("cp.async.bulk.commit_group;" ::: "memory"); } __syncwarp(); }
#define PUBLISH_O() { if (h) WARP_STORE(&tm_os, pO, jj * 128 + 64, mm * 128) else { fence_proxy_async_smem(); bar_arrive<BAR_O, 288>(); } }
#define X_OUT(pc, on) { \
      PMASKS(on, X_BIT(l)); \
      _Pragma("unroll") for (int j = (pc) * 4; j < (pc) * 4 + 4; j++) \
        stsm_x4(pK + (pc) * SLOT + srowoff + ((((uint32_t)(j & 3) << 5) + lhi) ^ lsw), \
                PBIT0(pack_bf16(S1[j * 8 + 0], S1[j * 8 + 1])), PBIT0(pack_bf16(S1[j * 8 + 2], S1[j * 8 + 3])), \
                PBIT1(pack_bf16(S1[j * 8 + 4], S1[j * 8 + 5])), PBIT1(pack_bf16(S1[j * 8 + 6], S1[j * 8 + 7]))); }
#define REST_P1(SKEW) { \
      mbar_wait(bar_stat2, par); \
      LNSTEP(S1, 1); \
      _Pragma("unroll 1") while (ub < bar_full + 256) { \
        if (ub == bar_full + 256 - 8 * (SKEW) && wg == 0) bar_sync<BAR_SKEW, 256>(); \
        QSTEP(S1, RA_CUR, 1, {}); \
        if (ub == bar_full + 248 && wg == 1) bar_arrive<BAR_SKEW, 256>(); \
        QREL(); \
      } \
      hbase += 256; \
      mbar_wait(bar_done + (31 - (SKEW)) * 8, par);        \
      wgmma_wait<0>(); \
      ACC_FENCE(S1, 96); \
      REL(bar_done + 31 * 8); \
      PROF(13); }
#define FOLD(tile, rd) { \
          LANE_CONSTS(); \
          float d[32]; \
          ACC_DEF(d, 32); \
          mbar_wait(bar_phi + (rd) * 8, 0); \
          wgmma_fence(); \
          _Pragma("unroll") for (int i = 0; i < 2; i++) { \
            const uint64_t da = make_desc((tile) + wg * 8192 + i * 64, 16, 1024); \
            const uint64_t db = make_desc(sbase + OFF_PHI + wg * 4096 + i * 2048, 16, 512) ^ (3ull << 62); \
            wgmma_n32<0>(d + i * 16, da, db); wgmma_n32<1>(d + i * 16, da + 2, db + 64); \
          } \
          wgmma_commit(); \
          PUMP0(); \
          ACC_FENCE(d, 32); \
          bar_wg(wg); \
          _Pragma("unroll") for (int i = 0; i < 4; i++) { \
            const float* x = d + (i & 1) * 8 + (i >> 1) * 2; \
            sts128((tile) + wg * 8192 + ((warp & 3) * 16 + (i >> 1) * 8 + g) * 128 + (((2 * t + (i & 1)) ^ g) << 4), \
                   pack_bf16(x[0], x[1]), pack_bf16(x[4], x[5]), pack_bf16(x[16], x[17]), pack_bf16(x[20], x[21])); \
          } \
          fence_proxy_async_smem(); \
          bar_arrive<BAR_WF + 3 * (rd), 288>(); }
#define LOAD_X0(base) \
      _Pragma("unroll") for (int j = 0; j < 8; j++) { \
        uint32_t x0, x1, x2, x3; \
        ldsm_x4((base) + (j >> 2) * SLOT + srowoff + ((((uint32_t)(j & 3) << 5) + lhi) ^ lsw), x0, x1, x2, x3); \
        S1[j * 8 + 0] = bf_lo(x0); S1[j * 8 + 1] = bf_hi(x0); S1[j * 8 + 2] = bf_lo(x1); S1[j * 8 + 3] = bf_hi(x1); \
        S1[j * 8 + 4] = bf_lo(x2); S1[j * 8 + 5] = bf_hi(x2); S1[j * 8 + 6] = bf_lo(x3); S1[j * 8 + 7] = bf_hi(x3); \
      }
#define LOAD_X() { \
      wgmma_wait<0>(); \
      mbar_wait(bar_xr, par); \
      LOAD_X0(sbase + OFF_RA); \
      ACC_FENCE(S1, 64); \
      __syncwarp(); if (elect_one()) mbar_arrive_local(bar_lx); }

    float S1[96];
#pragma unroll
    for (int i = 0; i < 64; i++) S1[i] = 0.f;
#pragma unroll 1
    for (int l = 0; l < NLAYERS; l++) {
      const uint32_t par = l & 1;
      bar_wg(wg);
      PROF(0);
      uint32_t ub = bar_full;
      const bool hsend = (warp == 7) && (mm < 15);
      const uint32_t hbit = (NLAYERS > 2) ? (l == 0) : (ep1 & 1);
      float S0[96];
      {
        LANE_CONSTS();
        ACC_DEF(S0, 96);
        QSTEP(S0, dA0 + (OFF_S >> 4), 0, {});
        ub += 8;
        PROF(1);
        if (l == 0) { mbar_wait(ub, 0); LOAD_X0(pK); }
        else { X_OUT(1, false); fence_proxy_async_smem(); }
        SCHED_FENCE();
        {
          float a0 = S1[0], a1 = S1[2], b0 = S1[1], b1 = S1[3];
#pragma unroll
          for (int i = 4; i < 64; i += 4) { a0 += S1[i]; b0 += S1[i + 1]; a1 += S1[i + 2]; b1 += S1[i + 3]; }
          a0 += b0; a1 += b1;
          a0 += __shfl_xor_sync(0xffffffffu, a0, 1); a1 += __shfl_xor_sync(0xffffffffu, a1, 1);
          a0 += __shfl_xor_sync(0xffffffffu, a0, 2); a1 += __shfl_xor_sync(0xffffffffu, a1, 2);
          a0 *= (1.f / 128.f); a1 *= (1.f / 128.f);
          asm volatile("" : "+f"(a0), "+f"(a1));
          bar_wg(wg);
          QSTEP(S0, dA0 + ((OFF_S + SLOT) >> 4), 1, wgmma_wait<0>());
          REL(ub + 376); ub += 8;
          SCHED_FENCE();
          float q0 = 0.f, q1 = 0.f;
          b0 = 0.f; b1 = 0.f;
#pragma unroll
          for (int i = 0; i < 64; i += 4) {
            const float d0 = S1[i] - a0, d1 = S1[i + 1] - a0, d2 = S1[i + 2] - a1, d3 = S1[i + 3] - a1;
            q0 = fmaf(d0, d0, q0); b0 = fmaf(d1, d1, b0); q1 = fmaf(d2, d2, q1); b1 = fmaf(d3, d3, b1);
          }
          q0 += b0; q1 += b1;
          q0 += __shfl_xor_sync(0xffffffffu, q0, 1); q1 += __shfl_xor_sync(0xffffffffu, q1, 1);
          q0 += __shfl_xor_sync(0xffffffffu, q0, 2); q1 += __shfl_xor_sync(0xffffffffu, q1, 2);
          if (t < 2) st_b64(g_stats + (size_t)(mm * 128 + r0 + g + t * 8) * 8 + jj, __float_as_uint(t ? a1 : a0), (__float_as_uint(t ? q1 : q0) & ~3u) | STAT_TAG(l));
        }
        if (l) { asm volatile("cp.async.bulk.wait_group 0;" ::: "memory"); bar_arrive<BAR_O + 3, 288>(); }
        ACC_DEF(S1, 96);
        QSTEP(S1, dA0 + (OFF_S >> 4), 0, {});
        QREL();
        QSTEP(S1, dA0 + ((OFF_S + SLOT) >> 4), 1, {});
        QREL();
#pragma unroll 1
        for (int i = 0; i < 14; i++) {
          QSTEP(S0, RA_CUR, 1, {});
          if (i == 0) PROF(2);
          QREL();
        }
      }
      LANE_CONSTS();
      uint4* hbase = g_halo + (size_t)(mm * 8 + jj) * 512;
      mbar_wait(bar_stat, par);
      LNSTEP(S0, 0);
      wgmma_commit();
      const float rs0 = lds32f(sbase + OFF_ST + (r0 + g) * 4), rs1 = lds32f(sbase + OFF_ST + (r0 + g + 8) * 4);
      PUMP0();
      ACC_FENCE(S0, 96);
      PROF(3);
      if (!par) {
        constexpr uint32_t par = 0;
        uint32_t qa[16];
        DRAIN_A(S0, PUMP0());
#pragma unroll 1
        for (int h = 0; h < 2; h++) {
          const uint32_t pO = sbase + (h ? 3 : 12) * SLOT;
          PROF(4 + h * 12);
          const bool fold = (l == 0 && h == 0 && NLAYERS > 1);
          if (fold) FOLD(pO, 0) else if (h == 0) PUMPS(HPUMP1);
          LANE_CONSTS();
          uint4 hv[8];
#pragma unroll
          for (int i = 0; i < 8; i++) hv[i] = make_uint4(hbit, 0, 0, 0);
          const bool hrec = (warp == 0 && mm > 0);
          if (hrec) {
#pragma unroll
            for (int i = 0; i < 8; i++) hv[i] = ld_b128(hbase + lane - 8 * 512 + i * 32);
          }
          if (h) LOAD_X() else PUMPS(HPUMP2);
          const uint32_t halo = sbase + OFF_HALO;
          STG_WAIT();
          if (warp == 0) {
#pragma unroll 1
            for (int it = 0; it < (1 << 16); it++) {
              uint32_t bad = 0;
#pragma unroll
              for (int i = 0; i < 8; i++) bad |= hv[i].x ^ hbit;
              if (__all_sync(0xffffffffu, (bad & 1) == 0)) break;
#pragma unroll
              for (int i = 0; i < 8; i++) hv[i] = ld_b128(hbase + lane - 8 * 512 + i * 32);
            }
#pragma unroll
            for (int i = 0; i < 8; i++)
              stsm_x4(i < 4 ? halo + srowoff + ((((uint32_t)i << 5) + lhi) ^ lsw)
                            : halo + (srowoff >> 1) + (i >> 1) * 1024 + ((((uint32_t)(i & 1) << 5) + lhi) ^ lsw2), hv[i].x, hv[i].y, hv[i].z, hv[i].w);
            __syncwarp();
          }
          PROF(5 + h * 12);
          const uint32_t kb1 = pK + r0 * 128, vb1 = pV + r0 * 64;
          const uint32_t kb0 = r0 ? kb1 - 2048 : halo, vb0 = r0 ? vb1 - 1024 : halo + 2048;
          const uint32_t vhs = r0 ? 8192 : 1024;
          float s[2][4][4];
          {
            uint32_t kf[2][4][4];
#pragma unroll
            for (int i = 0; i < 8; i++) {
              const int hh = i >> 2, jb = i & 3;
              ldsm_x4(((jb < 2) ? kb0 : kb1) + ((jb & 1) * 8 + (lane & 7)) * 128 + ((hh * 64 + ((lane >> 3) << 4)) ^ lsw), kf[hh][jb][0], kf[hh][jb][1], kf[hh][jb][2], kf[hh][jb][3]);
              s[hh][jb][0] = s[hh][jb][1] = s[hh][jb][2] = s[hh][jb][3] = 0.f;
            }
#pragma unroll
            for (int ks = 0; ks < 2; ks++)
#pragma unroll
              for (int i = 0; i < 8; i++) {
                const int hh = i >> 2, jb = i & 3;
                mma_bf16(s[hh][jb], qa[hh * 8 + ks * 4], qa[hh * 8 + ks * 4 + 1], qa[hh * 8 + ks * 4 + 2], qa[hh * 8 + ks * 4 + 3], kf[hh][jb][ks * 2], kf[hh][jb][ks * 2 + 1]);
              }
          }
          PUMP();
          if (fold) bar_arrive<BAR_WF + 2, 288>();
          PROF(6 + h * 12);
          const bool e = g & 1, hb = (2 * t + (g & 1)) <= g;
          uint32_t vf[2][2][2][4];
#pragma unroll
          for (int i = 0; i < 8; i++) {
            const int hh = i >> 2, ks = (i >> 1) & 1, dp = i & 1;
            ldsm_x4_t((ks ? vb1 + hh * 8192 : vb0 + hh * vhs) + (lane & 15) * 64 + ((dp * 32 + lhi) ^ lsw2), vf[hh][ks][dp][0], vf[hh][ks][dp][1], vf[hh][ks][dp][2], vf[hh][ks][dp][3]);
          }
          float va[2][2], vb[2][2], mx[2][2];
#pragma unroll
          for (int hh = 0; hh < 2; hh++) {
            va[hh][0] = e ? s[hh][1][1] : s[hh][1][0];
            vb[hh][0] = hb ? (e ? s[hh][2][1] : s[hh][2][0]) : (e ? s[hh][0][1] : s[hh][0][0]);
            va[hh][1] = e ? s[hh][2][3] : s[hh][2][2];
            vb[hh][1] = hb ? (e ? s[hh][3][3] : s[hh][3][2]) : (e ? s[hh][1][3] : s[hh][1][2]);
          }
          if (warp == 0 && mm == 0) {
#pragma unroll
            for (int hh = 0; hh < 2; hh++) { va[hh][0] = -INFINITY; if (!hb) { vb[hh][0] = -INFINITY; vb[hh][1] = -INFINITY; } }
          }
#pragma unroll
          for (int i = 0; i < 4; i++) mx[i >> 1][i & 1] = fmaxf(va[i >> 1][i & 1], vb[i >> 1][i & 1]);
#pragma unroll
          for (int o = 1; o <= 2; o <<= 1)
#pragma unroll
            for (int i = 0; i < 4; i++) mx[i >> 1][i & 1] = fmaxf(mx[i >> 1][i & 1], __shfl_xor_sync(0xffffffffu, mx[i >> 1][i & 1], o));
          const float sc0 = rs0 * (0.17677669529663687f * LOG2E), sc1 = rs1 * (0.17677669529663687f * LOG2E);
#pragma unroll
          for (int i = 0; i < 4; i++) {
            const float sc = (i & 1) ? sc1 : sc0, m = mx[i >> 1][i & 1];
            va[i >> 1][i & 1] = ex2((va[i >> 1][i & 1] - m) * sc); vb[i >> 1][i & 1] = ex2((vb[i >> 1][i & 1] - m) * sc);
            mx[i >> 1][i & 1] = va[i >> 1][i & 1] + vb[i >> 1][i & 1];
          }
          if (h == 0 && ASITE) { PIN(&va[0][0], 4); PIN(&vb[0][0], 4); PIN(&mx[0][0], 4); PUMP1(); }
#pragma unroll
          for (int o = 1; o <= 2; o <<= 1)
#pragma unroll
            for (int i = 0; i < 4; i++) mx[i >> 1][i & 1] += __shfl_xor_sync(0xffffffffu, mx[i >> 1][i & 1], o);
          const uint32_t selA = e ? 0x1044 : 0x4410, selB = e ? 0x3244 : 0x4432, selL = hb ? 0x4444 : selB, selH = hb ? selB : 0x4444;
          float o[2][4][4];
          uint32_t pa[2][6];
#pragma unroll
          for (int hh = 0; hh < 2; hh++) {
            const float i0 = rcp_fast(mx[hh][0]), i1 = rcp_fast(mx[hh][1]);
            const uint32_t w0 = pack_bf16(va[hh][0] * i0, vb[hh][0] * i0), w1 = pack_bf16(va[hh][1] * i1, vb[hh][1] * i1);
            pa[hh][0] = __byte_perm(w0, 0, selL); pa[hh][1] = __byte_perm(w0, 0, selA); pa[hh][2] = __byte_perm(w1, 0, selL);
            pa[hh][3] = __byte_perm(w0, 0, selH); pa[hh][4] = __byte_perm(w1, 0, selA); pa[hh][5] = __byte_perm(w1, 0, selH);
#pragma unroll
            for (int dj = 0; dj < 4; dj++) { o[hh][dj][0] = o[hh][dj][1] = o[hh][dj][2] = o[hh][dj][3] = 0.f; }
          }
          PROF(7 + h * 12);
#pragma unroll
          for (int i = 0; i < 8; i++) mma_bf16(o[i >> 2][i & 3], pa[i >> 2][0], 0u, pa[i >> 2][1], pa[i >> 2][2], vf[i >> 2][0][(i >> 1) & 1][(i & 1) * 2], vf[i >> 2][0][(i >> 1) & 1][(i & 1) * 2 + 1]);
#pragma unroll
          for (int i = 0; i < 8; i++) mma_bf16(o[i >> 2][i & 3], pa[i >> 2][3], pa[i >> 2][4], 0u, pa[i >> 2][5], vf[i >> 2][1][(i >> 1) & 1][(i & 1) * 2], vf[i >> 2][1][(i >> 1) & 1][(i & 1) * 2 + 1]);
          if (h == 0) PUMP1() else mbar_wait(bar_done + 30 * 8, par);
          if (fold) mbar_wait(bar_phi, 1);
#pragma unroll
          for (int i = 0; i < 4; i++) {
            const int hh = i >> 1, dp = i & 1;
            PMASKS(h, O_BIT(l));
            stsm_x4(pO + srowoff + ((hh * 64 + dp * 32 + lhi) ^ lsw), PBIT0(pack_bf16(o[hh][dp * 2][0], o[hh][dp * 2][1])), PBIT0(pack_bf16(o[hh][dp * 2][2], o[hh][dp * 2][3])),
                    PBIT1(pack_bf16(o[hh][dp * 2 + 1][0], o[hh][dp * 2 + 1][1])), PBIT1(pack_bf16(o[hh][dp * 2 + 1][2], o[hh][dp * 2 + 1][3])));
          }
          PUBLISH_O();
          PROF(11 + h * 12);
          if (h) break;
          if (fold) { PUMPS(FPUMP); FOLD(pK, 1); }
          REST_P1(ASKEW);
          if (fold) mbar_wait(bar_phi + 8, 1);
          DRAIN_A(S1, {});
        }
      } else {
        constexpr uint32_t par = 1;
        float st[64];
        DRAIN_B(S0);
        if (warp < 2) sts128(sbase + OFF_ONES + warp * 512 + lane * 16, 0x3F803F80u, 0x3F803F80u, 0x3F803F80u, 0x3F803F80u);
        const float c0 = rs0 * LOG2E, c1 = rs1 * LOG2E;
#define KV_PART(hp, ...) { \
          float kv[20]; \
          ACC_DEF(kv, 20); \
          const uint64_t dp = make_desc(wg ? pK : sbase + 12 * SLOT, 16, 1024); \
          const uint64_t dv = (make_desc(pV + wg * 8192, OFF_ONES - OFF_S - SLOT - wg * 8192, 512) ^ (3ull << 62)); \
          constexpr uint64_t DVS = 64ull - (64ull << 16); \
          fence_proxy_async_smem(); \
          STG_ARRIVE(); \
          STG_WAIT(); \
          wgmma_fence(); \
          _Pragma("unroll") for (int ks = 0; ks < 8; ks++) { if (ks == 0) wgmma_n40<0, 1>(kv, dp, dv); else wgmma_n40<1, 1>(kv, dp + ks * 128, dv + ks * DVS); } \
          wgmma_commit(); \
          __VA_ARGS__; \
          ACC_FENCE(kv, 20); \
          float* kvg = g_kv[l >> 1] + (jj * 4 + (hp) * 2 + wg) * KVH + ((warp & 3) * 32 + lane) * 4; \
          _Pragma("unroll") for (int i = 0; i < 4; i++) red_v4(kvg + i * 512, kv[i * 4], kv[i * 4 + 1], kv[i * 4 + 2], kv[i * 4 + 3]); \
          if (t == 0) red_v4(kvg + 2048, kv[16], kv[17], kv[18], kv[19]); \
          bar_arrive<BAR_KV + (hp), 288>(); \
          STG_ARRIVE(); }
#pragma unroll 1
        for (int h = 0; h < 2; h++) {
          PROF(4 + h * 2);
          SITE(0);
          LANE_CONSTS();
          const uint32_t dsw = (uint32_t)(g ^ (2 * t)) << 4, dst = ((t & 2) ? pK : sbase + 12 * SLOT) + (r0 + g) * 128;
          float e[16], f[16];
          float mn0 = rmin16(st);
          asm volatile("" : "+f"(mn0)); SCHED_FENCE();
          float sa = exps16(e, st, -c0, mn0 * c0), mx0 = rmax16(st);
          asm volatile("" : "+f"(sa), "+f"(mx0)); PIN(e, 16); SITE(1);
          if (h) STG_WAIT();
          store16(e, sa, dst, dsw, 4);
          float sb = exps16(f, st, c0, -mx0 * c0), mn1 = rmin16(st + 2);
          asm volatile("" : "+f"(sb), "+f"(mn1)); PIN(f, 16); SITE(2);
          store16(f, sb, dst, dsw, 0);
          float sc = exps16(e, st + 2, -c1, mn1 * c1), mx1 = rmax16(st + 2);
          asm volatile("" : "+f"(sc), "+f"(mx1)); PIN(e, 16); SITE(3);
          store16(e, sc, dst + 1024, dsw, 4);
          float sd = exps16(f, st + 2, c1, -mx1 * c1);
          asm volatile("" : "+f"(sd)); PIN(f, 16); SITE(4);
          store16(f, sd, dst + 1024, dsw, 0);
          PROF(5 + h * 2);
          if (h) break;
          KV_PART(0, PUMP0());
#pragma unroll
          for (int i = 0; i < 32; i++) st[i] = st[32 + i];
        }
        REST_P1(1);
        {
          LANE_CONSTS();
          DRAIN_B(S1);
          PROF(16);
          KV_PART(1, wgmma_wait<0>());
          PROF(17);
        }
#pragma unroll 1
        for (int h = 0; h < 2; h++) {
          const uint32_t pO = sbase + (h ? 3 : 12) * SLOT, pP = sbase + (h ? 9 : 10) * SLOT, pT = sbase + (h ? 11 : 8) * SLOT;
          LANE_CONSTS();
          const float4* kvg = reinterpret_cast<const float4*>(g_kv[l >> 1] + (jj * 4 + h * 2 + wg) * KVH) + (warp & 3) * 32 + lane;
          float4 v[5];
#define KV_LOAD() { \
            mbar_wait(bar_kvf + h * 8, l >> 1); \
            _Pragma("unroll") for (int i = 0; i < 4; i++) v[i] = __ldcg(kvg + i * 128); \
            v[4] = __ldcg(kvg + 512 - t); }
#pragma unroll
          for (int i = 0; i < 5; i++) v[i] = make_float4(0.f, 0.f, 0.f, 0.f);
          if (h == 0) KV_LOAD();
          const uint32_t dsw = (uint32_t)(g ^ (2 * t)) << 4, dst = ((t & 2) ? pP : pO) + (r0 + g) * 128;
          uint32_t fq[16];
          float m0 = rmin16(st);
          asm volatile("" : "+f"(m0)); SCHED_FENCE();
          expp16(fq, st, -c0, m0 * c0);
          float m1 = rmax16(st);
          PINU(fq, 8); asm volatile("" : "+f"(m1)); SCHED_FENCE();
          expp16(fq + 8, st, c0, -m1 * c0);
          m0 = rmin16(st + 2);
          PINU(fq + 8, 8); asm volatile("" : "+f"(m0));
          if (h == 0) STG_WAIT();
#pragma unroll
          for (int i = 0; i < 4; i++) sts128(dst + (((((i & 2) ? 0 : 4) + (i & 1)) << 4) ^ dsw), fq[i * 4], fq[i * 4 + 1], fq[i * 4 + 2], fq[i * 4 + 3]);
          expp16(fq, st + 2, -c1, m0 * c1);
          m1 = rmax16(st + 2);
          PINU(fq, 8); asm volatile("" : "+f"(m1)); SCHED_FENCE();
          expp16(fq + 8, st + 2, c1, -m1 * c1);
#pragma unroll
          for (int i = 0; i < 4; i++) sts128(dst + 1024 + (((((i & 2) ? 0 : 4) + (i & 1)) << 4) ^ dsw), fq[i * 4], fq[i * 4 + 1], fq[i * 4 + 2], fq[i * 4 + 3]);
          PROF(18 + h * 6);
          if (h) {
            wgmma_wait<0>();
            REL(bar_done + 32 * 8);
            PROF(25);
            KV_LOAD();
            PROF(26);
          }
          {
            const uint32_t kd = pT + wg * 8192 + ((warp & 3) * 16 + (lane & 15)) * 128;
#pragma unroll
            for (int i = 0; i < 2; i++) {
              const float4 a = v[i * 2], b = v[i * 2 + 1];
              stsm_x4(kd + ((i * 32 + lhi) ^ lsw), pack_bf16(a.x, a.y), pack_bf16(a.z, a.w), pack_bf16(b.x, b.y), pack_bf16(b.z, b.w));
            }
            stsm_x4(kd + ((64u + lhi) ^ lsw), pack_bf16(v[4].x, 1.f), pack_bf16(v[4].z, 1.f), 0u, 0u);
          }
          fence_proxy_async_smem();
          STG_ARRIVE();
          float o[4][20];
          ACC_DEF(o[0], 20); ACC_DEF(o[1], 20); ACC_DEF(o[2], 20); ACC_DEF(o[3], 20);
          STG_WAIT();
          PROF(19 + h * 14);
          wgmma_fence();
#pragma unroll
          for (int hh = 0; hh < 2; hh++) {
            const uint64_t da = make_desc((hh ? pP : pO) + wg * 8192, 16, 1024);
            const uint64_t db = make_desc(pT + hh * 8192, 16, 1024);
#pragma unroll
            for (int ks = 0; ks < 4; ks += 2) { wgmma_n40<0, 0>(o[hh * 2 + (ks >> 1)], da + ks * 2, db + ks * 128); wgmma_n40<1, 0>(o[hh * 2 + (ks >> 1)], da + ks * 2 + 2, db + ks * 128 + 128); }
          }
          wgmma_commit();
          wgmma_wait<0>();
          ACC_FENCE(o[0], 20); ACC_FENCE(o[1], 20); ACC_FENCE(o[2], 20); ACC_FENCE(o[3], 20);
          bar_wg(wg);
          PMASKS(h, O_BIT(l));
#pragma unroll
          for (int hh = 0; hh < 2; hh++) {
            const float* x = o[hh * 2];
            const float* y = o[hh * 2 + 1];
            const float rx0 = rcp_fast(x[17]), ry0 = rcp_fast(y[17]), rx1 = rcp_fast(x[19]), ry1 = rcp_fast(y[19]);
            const float i0 = rcp_fast(fmaf(x[16], rx0, y[16] * ry0) + 1e-6f), i1 = rcp_fast(fmaf(x[18], rx1, y[18] * ry1) + 1e-6f);
            const float ax0 = rx0 * i0, ay0 = ry0 * i0, ax1 = rx1 * i1, ay1 = ry1 * i1;
#pragma unroll
            for (int dp = 0; dp < 2; dp++)
              stsm_x4(pO + srowoff + ((hh * 64 + dp * 32 + lhi) ^ lsw),
                      PBIT0(pack_bf16(fmaf(x[dp * 8], ax0, y[dp * 8] * ay0), fmaf(x[dp * 8 + 1], ax0, y[dp * 8 + 1] * ay0))),
                      PBIT0(pack_bf16(fmaf(x[dp * 8 + 2], ax1, y[dp * 8 + 2] * ay1), fmaf(x[dp * 8 + 3], ax1, y[dp * 8 + 3] * ay1))),
                      PBIT1(pack_bf16(fmaf(x[dp * 8 + 4], ax0, y[dp * 8 + 4] * ay0), fmaf(x[dp * 8 + 5], ax0, y[dp * 8 + 5] * ay0))),
                      PBIT1(pack_bf16(fmaf(x[dp * 8 + 6], ax1, y[dp * 8 + 6] * ay1), fmaf(x[dp * 8 + 7], ax1, y[dp * 8 + 7] * ay1))));
          }
          PUBLISH_O();
          PROF(20 + h * 14);
          if (h) break;
          LOAD_X();
          bar_wg(wg);
          WSTEP();
#pragma unroll
          for (int i = 0; i < 32; i++) st[i] = st[32 + i];
        }
      }
      __syncwarp();
      if (elect_one()) mbar_arrive_local(bar_epi);
      bar_wg(wg);
#pragma unroll 1
      while (ub < bar_full + 384) {
        WSTEP();
        if (ub == bar_full + 8 * 41) { asm volatile("cp.async.bulk.wait_group.read 0;" ::: "memory"); PROF(35); }
        if (ub == bar_full + 8 * 42) PROF(36);
      }
      wgmma_wait<0>();
      ACC_FENCE(S1, 64);
      REL(bar_done + 47 * 8);
      PROF(37);
      {
        LANE_CONSTS();
        X_OUT(0, l < NLAYERS - 1);
        WARP_STORE(l < NLAYERS - 1 ? &tm_os : &tm_xo, pK, jj * 128, mm * 128 + (l < NLAYERS - 1 ? S_LEN : 0));
        if (l == NLAYERS - 1) {
          X_OUT(1, false);
          WARP_STORE(&tm_xo, pV, jj * 128 + 64, mm * 128);
          asm volatile("cp.async.bulk.wait_group 0;" ::: "memory");
        }
      }
#pragma unroll
      for (int i = 32; i < 64; i++) { uint32_t c; asm volatile("mov.b32 %0, %1;" : "=r"(c) : "f"(S1[i])); S1[i] = __uint_as_float(c); }
      PROF(38);
    }
    const int tid = threadIdx.x;
    if (tid == 0) {
      unsigned old = atomicAdd(&g_flags.done.v, 1);
      if (old == ep1 * NMAIN - 1) {
        asm volatile("st.relaxed.gpu.global.u32 [%0], %1;" :: "l"(&g_flags.epoch.v), "r"(ep1) : "memory");
      }
    }
    __syncwarp();
    cluster_sync();
  }
}

typedef CUresult (*PFN_encode)(CUtensorMap*, CUtensorMapDataType, cuuint32_t, void*, const cuuint64_t*, const cuuint64_t*,
                               const cuuint32_t*, const cuuint32_t*, CUtensorMapInterleave, CUtensorMapSwizzle,
                               CUtensorMapL2promotion, CUtensorMapFloatOOBfill);

CUtensorMap make_map(PFN_encode enc, const void* ptr, uint64_t inner, uint64_t outer, uint32_t box_inner, uint32_t box_outer,
                     CUtensorMapSwizzle swz = CU_TENSOR_MAP_SWIZZLE_128B) {
  CUtensorMap m;
  cuuint64_t dims[2] = {inner, outer};
  cuuint64_t strides[1] = {inner * 2};
  cuuint32_t box[2] = {box_inner, box_outer};
  cuuint32_t es[2] = {1, 1};
  enc(&m, CU_TENSOR_MAP_DATA_TYPE_BFLOAT16, 2, const_cast<void*>(ptr), dims, strides, box, es, CU_TENSOR_MAP_INTERLEAVE_NONE,
      swz, CU_TENSOR_MAP_L2_PROMOTION_L2_256B, CU_TENSOR_MAP_FLOAT_OOB_FILL_NONE);
  return m;
}

}

extern "C" void kernel_launch(void* const* d_in, const int* in_sizes, int n_in, void* d_out, int out_size) {
  (void)in_sizes; (void)n_in; (void)out_size;
  static PFN_encode enc = nullptr;
  if (!enc) {
    void* fn = nullptr;
    cudaDriverEntryPointQueryResult qr;
    cudaGetDriverEntryPoint("cuTensorMapEncodeTiled", &fn, cudaEnableDefault, &qr);
    enc = (PFN_encode)fn;
    cudaFuncSetAttribute(mega_kernel, cudaFuncAttributeMaxDynamicSharedMemorySize, SMEM_BYTES);
  }
  Params prm;
  prm.x0 = (const __nv_bfloat16*)d_in[0];
  prm.wA_qkv = (const __nv_bfloat16*)d_in[1];
  prm.wA_o = (const __nv_bfloat16*)d_in[2];
  prm.wB_qkv = (const __nv_bfloat16*)d_in[4];
  prm.wB_phi = (const __nv_bfloat16*)d_in[5];
  prm.wB_o = (const __nv_bfloat16*)d_in[6];
  prm.out = (__nv_bfloat16*)d_out;
  void *obuf = nullptr, *wf = nullptr;
  cudaGetSymbolAddress(&obuf, g_obuf);
  cudaGetSymbolAddress(&wf, g_wfold);
  CUtensorMap tm_x0 = make_map(enc, d_in[0], D_MODEL, S_LEN, 64, 128);
  CUtensorMap tm_xo = make_map(enc, d_out, D_MODEL, S_LEN, 64, 16);
  CUtensorMap tm_os = make_map(enc, obuf, D_MODEL, 2 * S_LEN, 64, 16);
  CUtensorMap tm_o = make_map(enc, obuf, D_MODEL, 2 * S_LEN, 64, 128);
  CUtensorMap tm_wf = make_map(enc, wf, 2048, D_MODEL, 64, 32);
  CUtensorMap tm_wqA = make_map(enc, d_in[1], 3 * D_MODEL, D_MODEL, 64, 32);
  CUtensorMap tm_wqB = make_map(enc, prm.wB_qkv, 3 * D_MODEL, D_MODEL, 64, 32);
  CUtensorMap tm_woA = make_map(enc, prm.wA_o, D_MODEL, D_MODEL, 64, 64);
  CUtensorMap tm_woB = make_map(enc, prm.wB_o, D_MODEL, D_MODEL, 64, 64);
  CUtensorMap tm_phi = make_map(enc, prm.wB_phi, 32, 1024, 32, 128, CU_TENSOR_MAP_SWIZZLE_64B);
  mega_kernel<<<NMAIN + NAUX, 384, SMEM_BYTES>>>(tm_x0, tm_xo, tm_os, tm_o, tm_wf, tm_wqA, tm_wqB, tm_woA, tm_woB, tm_phi, prm);
}
```

```cpp
#include <cuda_runtime.h>
#include <cuda.h>
#include <cuda_bf16.h>
#include <stdint.h>

#define NLAYERS 4

#define STAG1 300
#define HPUMP1 2
#define HPUMP2 2
#define ASKEW 2
#define FPUMP 2
#define PFGAP 100
#define POLLW 4
#define POLL0 0
#define POLLGAP 120
#define BMASK 0x1F
#define ASITE 1
namespace {

constexpr int S_LEN = 2048, D_MODEL = 1024;
constexpr int NAUX = 4, NMAIN = 128;
constexpr int SLOT = 16384;
constexpr int QST = 24576;
constexpr int OFF_RA = 6 * SLOT, OFF_S = 10 * SLOT;
constexpr int OFF_HALO = 13 * SLOT, OFF_LNB = OFF_HALO  , OFF_ONES = OFF_HALO + 3072;
constexpr int OFF_ST = OFF_HALO + 7168  , OFF_PHI = OFF_HALO + 8192;
constexpr int OFF_BAR = 14 * SLOT;
constexpr int OFF_LNA = OFF_BAR + 1024;
constexpr int SMEM_BYTES = OFF_LNA + 2048;
#define WO_ASLOT(par) ((par) ? 0x689C7BA3689C768Cull : 0x68C97BA368C9768Cull)
constexpr unsigned long long WO_BSLOT = 0x5432105421054210ull;
__device__ __forceinline__ int kslice(int j, int i) { return i < 2 ? 2 * j + i : (i < 9 ? 2 * ((j + i - 1) & 7) : 2 * ((j + i) & 7) + 1); }
__device__ __forceinline__ int wslice(int j, int s) { return 2 * ((j + s) & 7) + (s >> 3); }
constexpr int KVH = 5 * 128 * 4;

struct __align__(128) Flag { unsigned v; unsigned pad[31]; };
struct Flags {
  Flag xready[4][16];
  Flag oready[4][16];
  Flag kvready[4][8][16];
  Flag wfready[8];
  Flag done;
  Flag epoch;
};

__device__ Flags g_flags;
__device__ __nv_bfloat16 g_obuf[2 * S_LEN * D_MODEL];
#define O_BIT(l) ((epoch * NLAYERS + (l) + 1) & 1u)
#define X_BIT(l) ((epoch * (NLAYERS - 1) + (l) + 1) & 1u)
__device__ __nv_bfloat16 g_wfold[D_MODEL * 2048];
__device__ uint4 g_halo[16 * 8 * 512];
__device__ float g_kv[2][32 * KVH];
__device__ __align__(128) uint2 g_colsum[2][1536][2];
__device__ __align__(128) uint2 g_stats[S_LEN * 8];
#define STAT_TAG(l) ((ep1 * NLAYERS + (l) + 1) & 3u)

#define RETRY_COUNT()
#define PROFL 1
#define PROFW 0
#define KVFLAG 1
#define PROFT(i) do {} while (0)
#define PROF(i) do {} while (0)

__device__ __forceinline__ uint32_t smem_u32(const void* p) { return (uint32_t)__cvta_generic_to_shared(p); }
__device__ __forceinline__ bool elect_one() {
  uint32_t p;
  asm volatile("{\n.reg .pred p;\nelect.sync _|p, 0xffffffff;\nselp.u32 %0, 1, 0, p;\n}\n" : "=r"(p));
  return p != 0;
}
__device__ __forceinline__ void mbar_init(uint32_t bar, uint32_t cnt) {
  asm volatile("mbarrier.init.shared::cta.b64 [%0], %1;" :: "r"(bar), "r"(cnt));
}
__device__ __forceinline__ void mbar_expect_tx(uint32_t bar, uint32_t bytes) {
  asm volatile("mbarrier.arrive.expect_tx.shared::cta.b64 _, [%0], %1;" :: "r"(bar), "r"(bytes) : "memory");
}
#define mbar_wait(bar, parity) \
  asm volatile("{\n.reg .pred p, q;\nW_%=:\nmbarrier.try_wait.parity.shared::cta.b64 p, [%1], %2;\nadd.s32 %0, %0, -1;\n" \
               "setp.gt.and.s32 q, %0, 0, !p;\n@q bra.uni W_%=;\n}\n" : "+r"(budget) : "r"((uint32_t)(bar)), "r"((uint32_t)(parity)) : "memory")
#define mbar_wait_sl(bar, parity) \
  asm volatile("{\n.reg .pred p, q;\nW_%=:\nmbarrier.try_wait.parity.shared::cta.b64 p, [%1], %2, 20000;\nadd.s32 %0, %0, -64;\n" \
               "setp.gt.and.s32 q, %0, 0, !p;\n@q bra.uni W_%=;\n}\n" : "+r"(budget) : "r"((uint32_t)(bar)), "r"((uint32_t)(parity)) : "memory")
__device__ __forceinline__ void mbar_arrive_local(uint32_t bar) {
  asm volatile("mbarrier.arrive.shared::cta.b64 _, [%0];" :: "r"(bar) : "memory");
}
__device__ __forceinline__ void tma_load_2d(uint32_t dst, const CUtensorMap* tm, uint32_t bar, int c0, int c1) {
  asm volatile("cp.async.bulk.tensor.2d.shared::cluster.global.mbarrier::complete_tx::bytes [%0], [%1, {%3, %4}], [%2];"
               :: "r"(dst), "l"(tm), "r"(bar), "r"(c0), "r"(c1) : "memory");
}
__device__ __forceinline__ void tma_load_2d_mc(uint32_t dst, const CUtensorMap* tm, uint32_t bar, int c0, int c1) {
  asm volatile("cp.async.bulk.tensor.2d.shared::cluster.global.mbarrier::complete_tx::bytes.multicast::cluster [%0], [%1, {%3, %4}], [%2], %5;"
               :: "r"(dst), "l"(tm), "r"(bar), "r"(c0), "r"(c1), "h"((uint16_t)3) : "memory");
}
__device__ __forceinline__ void tma_store_2d(const CUtensorMap* tm, uint32_t src, int c0, int c1) {
  asm volatile("cp.async.bulk.tensor.2d.global.shared::cta.bulk_group [%0, {%2, %3}], [%1];"
               :: "l"(tm), "r"(src), "r"(c0), "r"(c1) : "memory");
}
__device__ __forceinline__ void bulk_commit_wait() {
  asm volatile("cp.async.bulk.commit_group;\ncp.async.bulk.wait_group 0;" ::: "memory");
}
__device__ __forceinline__ void prefetch_tmap(const CUtensorMap* tm) {
  asm volatile("prefetch.tensormap [%0];" :: "l"(tm) : "memory");
}
__device__ __forceinline__ void fence_proxy_async_global() { asm volatile("fence.proxy.async.global;" ::: "memory"); }
__device__ __forceinline__ void fence_proxy_async_smem() { asm volatile("fence.proxy.async.shared::cta;" ::: "memory"); }
__device__ __forceinline__ unsigned ld_relaxed(const unsigned* p) {
  unsigned v;
  asm volatile("ld.relaxed.gpu.global.u32 %0, [%1];" : "=r"(v) : "l"(p) : "memory");
  return v;
}
__device__ __forceinline__ void fence_acquire() { asm volatile("fence.acquire.gpu;" ::: "memory"); }
__device__ __forceinline__ void wait_flag(const unsigned* p, unsigned target) {
  int it = 0;
  while ((int)(ld_relaxed(p) - target) < 0 && ++it < (1 << 20)) {}
  fence_acquire();
}
__device__ __forceinline__ void signal_release(unsigned* p) {
  asm volatile("red.release.gpu.global.add.u32 [%0], 1;" :: "l"(p) : "memory");
}
template <int ID, int N> __device__ __forceinline__ void bar_arrive() { asm volatile("bar.arrive %0, %1;" :: "n"(ID), "n"(N) : "memory"); }
template <int ID, int N> __device__ __forceinline__ void bar_sync() { asm volatile("bar.sync %0, %1;" :: "n"(ID), "n"(N) : "memory"); }
__device__ __forceinline__ void bar_wg(int wg) { asm volatile("bar.sync %0, 128;" :: "r"(2 + wg) : "memory"); }
__device__ __forceinline__ void cluster_sync() {
  asm volatile("barrier.cluster.arrive.relaxed.aligned;\nbarrier.cluster.wait.aligned;" ::: "memory");
}
__device__ __forceinline__ void cluster_wait() { asm volatile("barrier.cluster.wait.acquire.aligned;" ::: "memory"); }
enum { BAR_KV = 4  , BAR_O = 7  , BAR_WF = 12  , BAR_SKEW = 13 };

__device__ __forceinline__ void wgmma_fence() { asm volatile("wgmma.fence.sync.aligned;" ::: "memory"); }
__device__ __forceinline__ void wgmma_commit() { asm volatile("wgmma.commit_group.sync.aligned;" ::: "memory"); }
template <int N> __device__ __forceinline__ void wgmma_wait() { asm volatile("wgmma.wait_group.sync.aligned %0;" :: "n"(N) : "memory"); }

template <int scale_d, int tnsp_b = 1> __device__ __forceinline__ void wgmma_n192(float* d, uint64_t descA, uint64_t descB) {
  asm volatile("{\n.reg .pred p;\nsetp.ne.b32 p, %98, 0;\n"
               "wgmma.mma_async.sync.aligned.m64n192k16.f32.bf16.bf16 {%0,%1,%2,%3,%4,%5,%6,%7,%8,%9,%10,%11,%12,%13,%14,%15,%16,%17,%18,%19,%20,%21,%22,%23,%24,%25,%26,%27,%28,%29,%30,%31,%32,%33,%34,%35,%36,%37,%38,%39,%40,%41,%42,%43,%44,%45,%46,%47,%48,%49,%50,%51,%52,%53,%54,%55,%56,%57,%58,%59,%60,%61,%62,%63,%64,%65,%66,%67,%68,%69,%70,%71,%72,%73,%74,%75,%76,%77,%78,%79,%80,%81,%82,%83,%84,%85,%86,%87,%88,%89,%90,%91,%92,%93,%94,%95}, %96, %97, p, 1, 1, 0, %99;\n}\n"
               : "+f"(d[0]), "+f"(d[1]), "+f"(d[2]), "+f"(d[3]), "+f"(d[4]), "+f"(d[5]), "+f"(d[6]), "+f"(d[7]), "+f"(d[8]), "+f"(d[9]), "+f"(d[10]), "+f"(d[11]), "+f"(d[12]), "+f"(d[13]), "+f"(d[14]), "+f"(d[15]), "+f"(d[16]), "+f"(d[17]), "+f"(d[18]), "+f"(d[19]), "+f"(d[20]), "+f"(d[21]), "+f"(d[22]), "+f"(d[23]), "+f"(d[24]), "+f"(d[25]), "+f"(d[26]), "+f"(d[27]), "+f"(d[28]), "+f"(d[29]), "+f"(d[30]), "+f"(d[31]), "+f"(d[32]), "+f"(d[33]), "+f"(d[34]), "+f"(d[35]), "+f"(d[36]), "+f"(d[37]), "+f"(d[38]), "+f"(d[39]), "+f"(d[40]), "+f"(d[41]), "+f"(d[42]), "+f"(d[43]), "+f"(d[44]), "+f"(d[45]), "+f"(d[46]), "+f"(d[47]), "+f"(d[48]), "+f"(d[49]), "+f"(d[50]), "+f"(d[51]), "+f"(d[52]), "+f"(d[53]), "+f"(d[54]), "+f"(d[55]), "+f"(d[56]), "+f"(d[57]), "+f"(d[58]), "+f"(d[59]), "+f"(d[60]), "+f"(d[61]), "+f"(d[62]), "+f"(d[63]), "+f"(d[64]), "+f"(d[65]), "+f"(d[66]), "+f"(d[67]), "+f"(d[68]), "+f"(d[69]), "+f"(d[70]), "+f"(d[71]), "+f"(d[72]), "+f"(d[73]), "+f"(d[74]), "+f"(d[75]), "+f"(d[76]), "+f"(d[77]), "+f"(d[78]), "+f"(d[79]), "+f"(d[80]), "+f"(d[81]), "+f"(d[82]), "+f"(d[83]), "+f"(d[84]), "+f"(d[85]), "+f"(d[86]), "+f"(d[87]), "+f"(d[88]), "+f"(d[89]), "+f"(d[90]), "+f"(d[91]), "+f"(d[92]), "+f"(d[93]), "+f"(d[94]), "+f"(d[95])
               : "l"(descA), "l"(descB), "n"(scale_d), "n"(tnsp_b));
}
template <int scale_d> __device__ __forceinline__ void wgmma4_n192(float* d, uint32_t da, uint32_t db) {
#define R_ "{%0,%1,%2,%3,%4,%5,%6,%7,%8,%9,%10,%11,%12,%13,%14,%15,%16,%17,%18,%19,%20,%21,%22,%23,%24,%25,%26,%27,%28,%29,%30,%31,%32,%33,%34,%35,%36,%37,%38,%39,%40,%41,%42,%43,%44,%45,%46,%47,%48,%49,%50,%51,%52,%53,%54,%55,%56,%57,%58,%59,%60,%61,%62,%63,%64,%65,%66,%67,%68,%69,%70,%71,%72,%73,%74,%75,%76,%77,%78,%79,%80,%81,%82,%83,%84,%85,%86,%87,%88,%89,%90,%91,%92,%93,%94,%95}"
  asm volatile("{\n.reg .pred p, q;\n.reg .b64 a, b;\nsetp.ne.b32 p, %98, 0;\nsetp.eq.b32 q, 0, 0;\nmov.b64 a, {%96, 0x40000040};\nmov.b64 b, {%97, 0x40000040};\n"
               "wgmma.mma_async.sync.aligned.m64n192k16.f32.bf16.bf16 " R_ ", a, b, p, 1, 1, 0, 1;\nadd.s64 a, a, 2;\nadd.s64 b, b, 128;\n"
               "wgmma.mma_async.sync.aligned.m64n192k16.f32.bf16.bf16 " R_ ", a, b, q, 1, 1, 0, 1;\nadd.s64 a, a, 2;\nadd.s64 b, b, 128;\n"
               "wgmma.mma_async.sync.aligned.m64n192k16.f32.bf16.bf16 " R_ ", a, b, q, 1, 1, 0, 1;\nadd.s64 a, a, 2;\nadd.s64 b, b, 128;\n"
               "wgmma.mma_async.sync.aligned.m64n192k16.f32.bf16.bf16 " R_ ", a, b, q, 1, 1, 0, 1;\n}\n"
               : "+f"(d[0]), "+f"(d[1]), "+f"(d[2]), "+f"(d[3]), "+f"(d[4]), "+f"(d[5]), "+f"(d[6]), "+f"(d[7]), "+f"(d[8]), "+f"(d[9]), "+f"(d[10]), "+f"(d[11]), "+f"(d[12]), "+f"(d[13]), "+f"(d[14]), "+f"(d[15]), "+f"(d[16]), "+f"(d[17]), "+f"(d[18]), "+f"(d[19]), "+f"(d[20]), "+f"(d[21]), "+f"(d[22]), "+f"(d[23]), "+f"(d[24]), "+f"(d[25]), "+f"(d[26]), "+f"(d[27]), "+f"(d[28]), "+f"(d[29]), "+f"(d[30]), "+f"(d[31]), "+f"(d[32]), "+f"(d[33]), "+f"(d[34]), "+f"(d[35]), "+f"(d[36]), "+f"(d[37]), "+f"(d[38]), "+f"(d[39]), "+f"(d[40]), "+f"(d[41]), "+f"(d[42]), "+f"(d[43]), "+f"(d[44]), "+f"(d[45]), "+f"(d[46]), "+f"(d[47]), "+f"(d[48]), "+f"(d[49]), "+f"(d[50]), "+f"(d[51]), "+f"(d[52]), "+f"(d[53]), "+f"(d[54]), "+f"(d[55]), "+f"(d[56]), "+f"(d[57]), "+f"(d[58]), "+f"(d[59]), "+f"(d[60]), "+f"(d[61]), "+f"(d[62]), "+f"(d[63]), "+f"(d[64]), "+f"(d[65]), "+f"(d[66]), "+f"(d[67]), "+f"(d[68]), "+f"(d[69]), "+f"(d[70]), "+f"(d[71]), "+f"(d[72]), "+f"(d[73]), "+f"(d[74]), "+f"(d[75]), "+f"(d[76]), "+f"(d[77]), "+f"(d[78]), "+f"(d[79]), "+f"(d[80]), "+f"(d[81]), "+f"(d[82]), "+f"(d[83]), "+f"(d[84]), "+f"(d[85]), "+f"(d[86]), "+f"(d[87]), "+f"(d[88]), "+f"(d[89]), "+f"(d[90]), "+f"(d[91]), "+f"(d[92]), "+f"(d[93]), "+f"(d[94]), "+f"(d[95])
               : "r"(da), "r"(db), "n"(scale_d));
#undef R_
}
template <int scale_d> __device__ __forceinline__ void wgmma4_n128(float* d, uint32_t da, uint32_t db) {
#define R_ "{%0,%1,%2,%3,%4,%5,%6,%7,%8,%9,%10,%11,%12,%13,%14,%15,%16,%17,%18,%19,%20,%21,%22,%23,%24,%25,%26,%27,%28,%29,%30,%31,%32,%33,%34,%35,%36,%37,%38,%39,%40,%41,%42,%43,%44,%45,%46,%47,%48,%49,%50,%51,%52,%53,%54,%55,%56,%57,%58,%59,%60,%61,%62,%63}"
  asm volatile("{\n.reg .pred p, q;\n.reg .b64 a, b;\nsetp.ne.b32 p, %66, 0;\nsetp.eq.b32 q, 0, 0;\nmov.b64 a, {%64, 0x40000040};\nmov.b64 b, {%65, 0x40000040};\n"
               "wgmma.mma_async.sync.aligned.m64n128k16.f32.bf16.bf16 " R_ ", a, b, p, 1, 1, 0, 1;\nadd.s64 a, a, 2;\nadd.s64 b, b, 128;\n"
               "wgmma.mma_async.sync.aligned.m64n128k16.f32.bf16.bf16 " R_ ", a, b, q, 1, 1, 0, 1;\nadd.s64 a, a, 2;\nadd.s64 b, b, 128;\n"
               "wgmma.mma_async.sync.aligned.m64n128k16.f32.bf16.bf16 " R_ ", a, b, q, 1, 1, 0, 1;\nadd.s64 a, a, 2;\nadd.s64 b, b, 128;\n"
               "wgmma.mma_async.sync.aligned.m64n128k16.f32.bf16.bf16 " R_ ", a, b, q, 1, 1, 0, 1;\n}\n"
               : "+f"(d[0]), "+f"(d[1]), "+f"(d[2]), "+f"(d[3]), "+f"(d[4]), "+f"(d[5]), "+f"(d[6]), "+f"(d[7]), "+f"(d[8]), "+f"(d[9]), "+f"(d[10]), "+f"(d[11]), "+f"(d[12]), "+f"(d[13]), "+f"(d[14]), "+f"(d[15]), "+f"(d[16]), "+f"(d[17]), "+f"(d[18]), "+f"(d[19]), "+f"(d[20]), "+f"(d[21]), "+f"(d[22]), "+f"(d[23]), "+f"(d[24]), "+f"(d[25]), "+f"(d[26]), "+f"(d[27]), "+f"(d[28]), "+f"(d[29]), "+f"(d[30]), "+f"(d[31]), "+f"(d[32]), "+f"(d[33]), "+f"(d[34]), "+f"(d[35]), "+f"(d[36]), "+f"(d[37]), "+f"(d[38]), "+f"(d[39]), "+f"(d[40]), "+f"(d[41]), "+f"(d[42]), "+f"(d[43]), "+f"(d[44]), "+f"(d[45]), "+f"(d[46]), "+f"(d[47]), "+f"(d[48]), "+f"(d[49]), "+f"(d[50]), "+f"(d[51]), "+f"(d[52]), "+f"(d[53]), "+f"(d[54]), "+f"(d[55]), "+f"(d[56]), "+f"(d[57]), "+f"(d[58]), "+f"(d[59]), "+f"(d[60]), "+f"(d[61]), "+f"(d[62]), "+f"(d[63])
               : "r"(da), "r"(db), "n"(scale_d));
#undef R_
}
template <int scale_d> __device__ __forceinline__ void wgmma_n32(float* d, uint64_t descA, uint64_t descB) {
  asm volatile("{\n.reg .pred p;\nsetp.ne.b32 p, %18, 0;\n"
               "wgmma.mma_async.sync.aligned.m64n32k16.f32.bf16.bf16 {%0,%1,%2,%3,%4,%5,%6,%7,%8,%9,%10,%11,%12,%13,%14,%15}, %16, %17, p, 1, 1, 0, 1;\n}\n"
               : "+f"(d[0]), "+f"(d[1]), "+f"(d[2]), "+f"(d[3]), "+f"(d[4]), "+f"(d[5]), "+f"(d[6]), "+f"(d[7]), "+f"(d[8]), "+f"(d[9]), "+f"(d[10]), "+f"(d[11]), "+f"(d[12]), "+f"(d[13]), "+f"(d[14]), "+f"(d[15])
               : "l"(descA), "l"(descB), "n"(scale_d));
}
template <int scale_d, int tnsp_a> __device__ __forceinline__ void wgmma_n40(float* d, uint64_t descA, uint64_t descB) {
  asm volatile("{\n.reg .pred p;\nsetp.ne.b32 p, %22, 0;\n"
               "wgmma.mma_async.sync.aligned.m64n40k16.f32.bf16.bf16 {%0,%1,%2,%3,%4,%5,%6,%7,%8,%9,%10,%11,%12,%13,%14,%15,%16,%17,%18,%19}, %20, %21, p, 1, 1, %23, 1;\n}\n"
               : "+f"(d[0]), "+f"(d[1]), "+f"(d[2]), "+f"(d[3]), "+f"(d[4]), "+f"(d[5]), "+f"(d[6]), "+f"(d[7]), "+f"(d[8]), "+f"(d[9]), "+f"(d[10]), "+f"(d[11]), "+f"(d[12]), "+f"(d[13]), "+f"(d[14]), "+f"(d[15]), "+f"(d[16]), "+f"(d[17]), "+f"(d[18]), "+f"(d[19])
               : "l"(descA), "l"(descB), "n"(scale_d), "n"(tnsp_a));
}
__device__ __forceinline__ uint64_t make_desc(uint32_t addr, uint32_t lbo_bytes, uint32_t sbo_bytes) {
  return (uint64_t)((addr & 0x3FFFF) >> 4) | ((uint64_t)(lbo_bytes >> 4) << 16) | ((uint64_t)(sbo_bytes >> 4) << 32) | (1ull << 62);
}

__device__ __forceinline__ void ldsm_x4(uint32_t addr, uint32_t& r0, uint32_t& r1, uint32_t& r2, uint32_t& r3) {
  asm volatile("ldmatrix.sync.aligned.m8n8.x4.shared.b16 {%0,%1,%2,%3}, [%4];" : "=r"(r0), "=r"(r1), "=r"(r2), "=r"(r3) : "r"(addr) : "memory");
}
__device__ __forceinline__ void ldsm_x4_t(uint32_t addr, uint32_t& r0, uint32_t& r1, uint32_t& r2, uint32_t& r3) {
  asm volatile("ldmatrix.sync.aligned.m8n8.x4.trans.shared.b16 {%0,%1,%2,%3}, [%4];" : "=r"(r0), "=r"(r1), "=r"(r2), "=r"(r3) : "r"(addr) : "memory");
}
__device__ __forceinline__ void stsm_x4(uint32_t addr, uint32_t r0, uint32_t r1, uint32_t r2, uint32_t r3) {
  asm volatile("stmatrix.sync.aligned.m8n8.x4.shared.b16 [%0], {%1,%2,%3,%4};" :: "r"(addr), "r"(r0), "r"(r1), "r"(r2), "r"(r3) : "memory");
}
__device__ __forceinline__ void sts128(uint32_t addr, uint32_t a, uint32_t b, uint32_t c, uint32_t d) {
  asm volatile("st.shared.v4.u32 [%0], {%1,%2,%3,%4};" :: "r"(addr), "r"(a), "r"(b), "r"(c), "r"(d) : "memory");
}
__device__ __forceinline__ float lds32f(uint32_t addr) {
  float v;
  asm volatile("ld.shared.f32 %0, [%1];" : "=f"(v) : "r"(addr) : "memory");
  return v;
}
__device__ __forceinline__ void sts32f(uint32_t addr, float a) {
  asm volatile("st.shared.f32 [%0], %1;" :: "r"(addr), "f"(a) : "memory");
}
__device__ __forceinline__ void mma_bf16(float (&c)[4], uint32_t a0, uint32_t a1, uint32_t a2, uint32_t a3, uint32_t b0, uint32_t b1) {
  asm volatile("mma.sync.aligned.m16n8k16.row.col.f32.bf16.bf16.f32 {%0,%1,%2,%3}, {%4,%5,%6,%7}, {%8,%9}, {%0,%1,%2,%3};"
               : "+f"(c[0]), "+f"(c[1]), "+f"(c[2]), "+f"(c[3]) : "r"(a0), "r"(a1), "r"(a2), "r"(a3), "r"(b0), "r"(b1));
}
__device__ __forceinline__ uint32_t pack_bf16(float lo, float hi) {
  uint32_t r;
  asm("cvt.rn.bf16x2.f32 %0, %1, %2;" : "=r"(r) : "f"(hi), "f"(lo));
  return r;
}
__device__ __forceinline__ float bf_lo(uint32_t v) { return __uint_as_float(v << 16); }
__device__ __forceinline__ float bf_hi(uint32_t v) { return __uint_as_float(v & 0xFFFF0000u); }
__device__ __forceinline__ void split3(float x, uint32_t& h, uint32_t& m, uint32_t& l) {
  h = pack_bf16(x, 0.f); x -= bf_lo(h);
  m = pack_bf16(x, 0.f); x -= bf_lo(m);
  l = pack_bf16(x, 0.f);
}
__device__ __forceinline__ float ex2(float x) { float r; asm("ex2.approx.ftz.f32 %0, %1;" : "=f"(r) : "f"(x)); return r; }
__device__ __forceinline__ float rcp_fast(float x) { float r; asm("rcp.approx.ftz.f32 %0, %1;" : "=f"(r) : "f"(x)); return r; }
__device__ __forceinline__ void red_v4(float* p, float a, float b, float c, float d) {
  asm volatile("red.global.add.v4.f32 [%0], {%1, %2, %3, %4};" :: "l"(p), "f"(a), "f"(b), "f"(c), "f"(d) : "memory");
}
__device__ __forceinline__ uint4 ld_ll(const uint4* p) {
  uint4 v;
  asm volatile("{\n.reg .b64 a, b;\nld.relaxed.gpu.global.v2.b64 {a, b}, [%4];\nmov.b64 {%0, %1}, a;\nmov.b64 {%2, %3}, b;\n}\n"
               : "=r"(v.x), "=r"(v.y), "=r"(v.z), "=r"(v.w) : "l"(p) : "memory");
  return v;
}
__device__ __forceinline__ void st_b64(uint2* p, uint32_t a, uint32_t b) {
  asm volatile("{\n.reg .b64 v;\nmov.b64 v, {%1, %2};\nst.relaxed.gpu.global.b64 [%0], v;\n}\n" :: "l"(p), "r"(a), "r"(b) : "memory");
}
__device__ __forceinline__ void st_b128(uint4* p, uint32_t a, uint32_t b, uint32_t c, uint32_t d) {
  asm volatile("{\n.reg .b128 v;\nmov.b128 v, {%1, %2, %3, %4};\nst.relaxed.gpu.global.b128 [%0], v;\n}\n" :: "l"(p), "r"(a), "r"(b), "r"(c), "r"(d) : "memory");
}
__device__ __forceinline__ uint4 ld_b128(const uint4* p) {
  uint4 v;
  asm volatile("{\n.reg .b128 v;\nld.relaxed.gpu.global.b128 v, [%4];\nmov.b128 {%0, %1, %2, %3}, v;\n}\n" : "=r"(v.x), "=r"(v.y), "=r"(v.z), "=r"(v.w) : "l"(p) : "memory");
  return v;
}

constexpr float LOG2E = 1.4426950408889634f;

struct Params {
  const __nv_bfloat16* x0;
  const __nv_bfloat16* wA_qkv;
  const __nv_bfloat16* wA_o;
  const __nv_bfloat16* wB_qkv;
  const __nv_bfloat16* wB_phi;
  const __nv_bfloat16* wB_o;
  __nv_bfloat16* out;
};

#define ACC_DEF(d, n) _Pragma("unroll") for (int i_ = 0; i_ < (n); i_++) asm volatile("" : "=f"(d[i_]))
#define ACC_FENCE(d, n) _Pragma("unroll") for (int i_ = 0; i_ < (n); i_++) asm volatile("" : "+f"(d[i_]) :: "memory")
#define PIN(a, n) _Pragma("unroll") for (int i_ = 0; i_ < (n); i_++) asm volatile("" : "+f"((a)[i_]))
#define PINU(a, n) _Pragma("unroll") for (int i_ = 0; i_ < (n); i_++) asm volatile("" : "+r"((a)[i_]))

#define STAGE64(acc, off, p0, KIND, SEND) { \
    uint32_t w_[4][4]; \
    _Pragma("unroll") for (int j_ = 0; j_ < 4; j_++) { \
      const int o_ = (off) + j_ * 8; \
      w_[j_][0] = pack_bf16(rs0 * acc[o_ + 0], rs0 * acc[o_ + 1]); \
      w_[j_][1] = pack_bf16(rs1 * acc[o_ + 2], rs1 * acc[o_ + 3]); \
      w_[j_][2] = pack_bf16(rs0 * acc[o_ + 4], rs0 * acc[o_ + 5]); \
      w_[j_][3] = pack_bf16(rs1 * acc[o_ + 6], rs1 * acc[o_ + 7]); \
    } \
    if ((SEND) && hsend) { \
      _Pragma("unroll") for (int j_ = 0; j_ < 4; j_++) { \
        w_[j_][0] = (w_[j_][0] & ~1u) | hbit; \
        st_b128(hbase + lane + ((KIND) * 4 + j_) * 32, w_[j_][0], w_[j_][1], w_[j_][2], w_[j_][3]); \
      } \
    } \
    _Pragma("unroll") for (int j_ = 0; j_ < 4; j_++) \
      stsm_x4((KIND) ? (p0) + (j_ >> 1) * 8192 + (srowoff >> 1) + ((((uint32_t)(j_ & 1) << 5) + lhi) ^ lsw2) \
                     : (p0) + srowoff + ((((uint32_t)j_ << 5) + lhi) ^ lsw), \
              w_[j_][0], w_[j_][1], w_[j_][2], w_[j_][3]); \
  }
#define RW(j) (((j) >> 1) * 4 + ((j) & 1))
__device__ __forceinline__ float rmax16(const float* p) {
  float m[4];
#pragma unroll
  for (int j = 0; j < 4; j++) m[j] = fmaxf(fmaxf(p[RW(j)], p[RW(j + 4)]), fmaxf(p[RW(j + 8)], p[RW(j + 12)]));
  const float r = fmaxf(fmaxf(m[0], m[1]), fmaxf(m[2], m[3]));
  return fmaxf(r, __shfl_xor_sync(0xffffffffu, r, 1));
}
__device__ __forceinline__ float rmin16(const float* p) {
  float m[4];
#pragma unroll
  for (int j = 0; j < 4; j++) m[j] = fminf(fminf(p[RW(j)], p[RW(j + 4)]), fminf(p[RW(j + 8)], p[RW(j + 12)]));
  const float r = fminf(fminf(m[0], m[1]), fminf(m[2], m[3]));
  return fminf(r, __shfl_xor_sync(0xffffffffu, r, 1));
}
__device__ __forceinline__ float exps16(float* o, const float* p, float c, float b) {
  float s[4];
#pragma unroll
  for (int j = 0; j < 16; j++) { o[j] = ex2(fmaf(p[RW(j)], c, b)); if (j < 4) s[j] = o[j]; else s[j & 3] += o[j]; }
  return (s[0] + s[1]) + (s[2] + s[3]);
}
__device__ __forceinline__ void store16(const float* e, float sum, uint32_t dst, uint32_t dsw, int c0) {
  const float inv = rcp_fast(sum + __shfl_xor_sync(0xffffffffu, sum, 1));
#pragma unroll
  for (int j = 0; j < 2; j++)
    sts128(dst + (((c0 + j) << 4) ^ dsw), pack_bf16(e[j * 8] * inv, e[j * 8 + 1] * inv), pack_bf16(e[j * 8 + 2] * inv, e[j * 8 + 3] * inv),
           pack_bf16(e[j * 8 + 4] * inv, e[j * 8 + 5] * inv), pack_bf16(e[j * 8 + 6] * inv, e[j * 8 + 7] * inv));
}
__device__ __forceinline__ void expp16(uint32_t* o, const float* p, float c, float b) {
#pragma unroll
  for (int j = 0; j < 8; j++) o[j] = pack_bf16(ex2(fmaf(p[4 * j], c, b)), ex2(fmaf(p[4 * j + 1], c, b)));
}
#define SCHED_FENCE() asm volatile("pmevent 0;" ::: "memory")

__global__ void __cluster_dims__(2, 1, 1) __launch_bounds__(384, 1)
mega_kernel(const __grid_constant__ CUtensorMap tm_x0, const __grid_constant__ CUtensorMap tm_xo, const __grid_constant__ CUtensorMap tm_os,
            const __grid_constant__ CUtensorMap tm_o, const __grid_constant__ CUtensorMap tm_wf,
            const __grid_constant__ CUtensorMap tm_wqA, const __grid_constant__ CUtensorMap tm_wqB,
            const __grid_constant__ CUtensorMap tm_woA, const __grid_constant__ CUtensorMap tm_woB,
            const __grid_constant__ CUtensorMap tm_phi, const Params prm) {
  extern __shared__ __align__(1024) uint8_t smem_raw[];
  const uint32_t sbase = smem_u32(smem_raw);
  const uint32_t bar_full = sbase + OFF_BAR;
  const uint32_t bar_done = bar_full + 384;
  const uint32_t bar_stat = bar_full + 768, bar_stat2 = bar_full + 776, bar_epi = bar_full + 784, bar_phi = bar_full + 936  ;
  const uint32_t bar_xr = bar_full + 800, bar_lx = bar_full + 808, bar_kvf = bar_full + 816  , bar_stg = bar_full + 832;
  const uint32_t bar_chk = bar_full + 848;

  const int warp = __shfl_sync(0xffffffffu, threadIdx.x >> 5, 0), lane = threadIdx.x & 31;
  uint32_t rank;
  asm volatile("mov.u32 %0, %%cluster_ctarank;" : "=r"(rank));
  const int cta = (int)blockIdx.x - NAUX;
  const int cl = cta >> 1;
  const int jj = cl & 7, cc = cl >> 3;
  const int mm = cc * 2 + (int)rank;

#define LOAD_EPOCH() const unsigned epoch = ld_relaxed(&g_flags.epoch.v), ep1 = epoch + 1; (void)epoch
  int budget = 1 << 22;

  if (cta >= 0) {
    {
      const int tx = threadIdx.x;
      const __nv_bfloat16* pf = (tx < 128) ? prm.x0 + (size_t)(mm * 128 + tx) * D_MODEL + jj * 128
                                           : prm.wA_qkv + (size_t)(jj * 128 + (tx & 63)) * 3072 + ((tx - 128) >> 6) * 1024 + jj * 128 + rank * 64;
      if (tx < 320) asm volatile("prefetch.global.L2 [%0];" :: "l"(pf));
      else if (tx == 320) prefetch_tmap(&tm_x0);
      else if (tx == 352) prefetch_tmap(&tm_wqA);
      else if (tx == 383) asm volatile("prefetch.global.L2 [%0];" :: "l"(&g_flags.epoch.v));
    }
    if (elect_one()) {
#pragma unroll
      for (int i = 0; i < 4; i++) {
        const int u = warp * 4 + i;
        mbar_init(bar_full + u * 8, ((u >= 4 && u < 11) || u > 40) ? 2 : 1); mbar_init(bar_done + u * 8, 16);
      }
      mbar_init(bar_stat + warp * 16, 0x111111181182ull >> (4 * warp) & 15);
      mbar_init(bar_stat + warp * 16 + 8, 0x111111121811ull >> (4 * warp) & 15);
      asm volatile("fence.mbarrier_init.release.cluster;" ::: "memory");
    }
    __syncthreads();
    asm volatile("barrier.cluster.arrive.relaxed.aligned;" ::: "memory");
  }

  if (cta < 0) {
    LOAD_EPOCH();
    const uint32_t buf = sbase + warp * SLOT, bar = sbase + OFF_BAR + warp * 16;
    const uint32_t lsw = (lane & 7) << 4, lhi = (lane >> 4) << 4, lrow = (lane & 15) * 128;
    const bool el = elect_one();
    if (el) {
      mbar_init(bar, 1); mbar_init(bar + 8, 1);
      asm volatile("fence.mbarrier_init.release.cluster;" ::: "memory");
    }
#pragma unroll 1
    for (int rd = 0; rd < (NLAYERS > 1 ? 5 : 2); rd++) {
      if (rd >= 2 && warp >= 8) break;
      const int tk = rd < 2 ? blockIdx.x * 12 + warp : blockIdx.x * 8 + warp;
      const int half = tk & 1;
      const int blk = rd < 2 ? (tk >> 1) * 2 + rd : (4 - rd) * 16 + (tk >> 1);
      const CUtensorMap* tm = rd < 2 ? &tm_wqA : (rd == 2 ? &tm_wqB : &tm_wf);
      const int j0 = (blk & 15) >> 1;
#define AUX_LOAD(n) { const uint32_t d_ = buf + ((n) & 1) * 8192, b_ = bar + ((n) & 1) * 8; const int r_ = kslice(j0, 2 * (n) + half) * 64; \
        mbar_expect_tx(b_, 8192); tma_load_2d(d_, tm, b_, blk * 64, r_); tma_load_2d(d_ + 4096, tm, b_, blk * 64, r_ + 32); }
      if (el) {
        if (rd == 3) { wait_flag(&g_flags.wfready[j0].v, ep1 * 16); fence_proxy_async_global(); }
        AUX_LOAD(0); AUX_LOAD(1);
      }
      __syncwarp();
      float cs[8][4];
#pragma unroll
      for (int i = 0; i < 8; i++) cs[i][0] = cs[i][1] = cs[i][2] = cs[i][3] = 0.f;
#pragma unroll 1
      for (int n = 0; n < 8; n++) {
        const uint32_t tb = buf + (n & 1) * 8192 + lrow;
        mbar_wait(bar + (n & 1) * 8, (n >> 1) & 1);
#pragma unroll
        for (int i = 0; i < 16; i++) {
          uint32_t b0, b1, b2, b3;
          ldsm_x4_t(tb + (i >> 2) * 2048 + (((i & 3) * 32 + lhi) ^ lsw), b0, b1, b2, b3);
          mma_bf16(cs[2 * (i & 3)], 0x3F803F80u, 0x3F803F80u, 0x3F803F80u, 0x3F803F80u, b0, b1);
          mma_bf16(cs[2 * (i & 3) + 1], 0x3F803F80u, 0x3F803F80u, 0x3F803F80u, 0x3F803F80u, b2, b3);
        }
        __syncwarp();
        if (el && n < 6) AUX_LOAD(n + 2);
        __syncwarp();
      }
      if (lane < 4) {
#pragma unroll
        for (int i = 0; i < 8; i++) st_b64(&g_colsum[rd >= 2][blk * 32 + i * 4 + lane][half], __float_as_uint(cs[i][0]), (__float_as_uint(cs[i][1]) & ~3u) | (ep1 & 3));
      }
      __syncwarp();
    }
  } else if (warp >= 8) {
    asm volatile("setmaxnreg.dec.sync.aligned.u32 40;");
    if (warp == 8) {
      const bool el = elect_one();
      cluster_wait();
      if (el) {
#pragma unroll 1
        for (int l = 0; l < NLAYERS; l++) {
          const uint32_t par = l & 1;
          const CUtensorMap* tqk = par ? &tm_wf : &tm_wqA;
          const CUtensorMap* tv = par ? &tm_wqB : &tm_wqA;
          const CUtensorMap* two = par ? &tm_woB : &tm_woA;
          if (l == 1) { LOAD_EPOCH(); wait_flag(&g_flags.wfready[jj].v, ep1 * 16); fence_proxy_async_global(); }
#pragma unroll 1
          for (int u = 0; u < 32; u++) {
            if (u >= 4) mbar_wait_sl(bar_done + (u - 4) * 8, par);
            else if (l) mbar_wait_sl(bar_done + (43 + u + (u >> 1)) * 8, par ^ 1);
            else if (u == 1) __nanosleep(STAG1);
            else if (u == 2) mbar_wait_sl(bar_full, 0);
            const uint32_t fb = bar_full + u * 8;
            const bool res = u < 4 ? (l || u >= 2) : (u < 11 || (u >= 18 && u < 22));
            mbar_expect_tx(fb, res ? QST : QST + SLOT);
            const int row = kslice(jj, u < 4 ? u & 1 : (u < 18 ? u - 2 : (u < 22 ? u - 6 : u - 20))) * 64 + (int)rank * 32;
            const int ps = u < 4 ? u >> 1 : (u >= 18), col = jj * 128 + ps * 64;
            const int c0 = par ? jj * 128 + (ps ? 0 : 1024) : col;
            const uint32_t dst = sbase + (u & 3) * QST + rank * 4096;
            tma_load_2d_mc(dst, tqk, fb, c0, row);
            tma_load_2d_mc(dst + 8192, tqk, fb, c0 + (par ? 64 : 1024), row);
            tma_load_2d_mc(dst + 16384, tv, fb, col + 2048, row);
            if (l == 0 && u < 4) PROFT(473 + u);
          }
#pragma unroll 1
          for (int s = 0; s < 16; s++) {
            if (s < 5) { if (s != 2 && s != 4) mbar_wait_sl(bar_done + (28 + s) * 8, par); }
            else if (s != 14) mbar_wait_sl(bar_done + (27 + s - (s == 15)) * 8, par);
            const uint32_t fb = bar_full + (32 + s) * 8;
            mbar_expect_tx(fb, (s && s < 8) ? 2 * SLOT : SLOT);
            tma_load_2d_mc(sbase + rank * 8192 + (uint32_t)((WO_BSLOT >> (4 * s)) & 15) * SLOT, two, fb, jj * 128 + (int)rank * 64, wslice(jj, s) * 64);
            if (s >= 5 && s < 8) {
              if (s == 5) { mbar_wait_sl(bar_full + 33 * 8, par); fence_proxy_async_global(); mbar_wait_sl(bar_epi, par); }
              tma_load_2d(sbase + (uint32_t)((WO_ASLOT(par) >> (4 * s)) & 15) * SLOT, &tm_o, fb, wslice(jj, s) * 64, mm * 128);
            }
          }
        }
      }
      __syncwarp();
    } else if (warp == 9) {
      const bool el = elect_one();
      if (el) {
        PROFT(472);
        tma_load_2d(sbase + OFF_S, &tm_x0, bar_full, jj * 128, mm * 128);
        __nanosleep(STAG1);
        tma_load_2d(sbase + OFF_S + SLOT, &tm_x0, bar_full + 8, jj * 128 + 64, mm * 128);
      }
      __syncwarp();
      LOAD_EPOCH();
#pragma unroll 1
      for (int lp = 0; lp < 2 * NLAYERS; lp++) {
        const int l = lp >> 1, ph = lp & 1;
        const uint32_t par = l & 1;
        const __nv_bfloat16* pb = g_obuf + ph * 64 + (size_t)(mm * 128 + (ph ? 0 : S_LEN) + (lane & 7) * 16 + (jj & 1) * 8) * D_MODEL + (jj >> 1) * 16;
        const CUtensorMap* tm = lp ? &tm_o : &tm_x0;
        const int row = mm * 128 + ((ph || !l) ? 0 : S_LEN);
        const uint32_t bit = ph ? O_BIT(l) : X_BIT(l - 1);
        const uint32_t slots = ph ? (uint32_t)(WO_ASLOT(par) >> 36) : 0x8769876u;
        uint32_t rdy = lp ? 0 : 0xFF;
        mbar_wait_sl(ph ? bar_epi : (l ? bar_done + 47 * 8 : bar_full), ph ? par : (l ? par ^ 1 : 0));
#pragma unroll 1
        for (int i = 0; i < 7; i++) {
          if (!((rdy >> i) & 1)) {
            const unsigned* pp = reinterpret_cast<const unsigned*>(pb + ((jj + i + 1 + ((lane >> 3) & (POLLW - 1))) & 7) * 128);
            if (i == 0) __nanosleep(POLL0);
            unsigned v0 = ld_relaxed(pp);
            __nanosleep(POLLGAP);
            unsigned v1 = ld_relaxed(pp);
            uint32_t no;
#pragma unroll 1
            for (int it = 0; it < (1 << 18); it++) {
              no = __ballot_sync(0xffffffffu, (v0 ^ bit) & 1);
              if (!(no & 0xFF)) break;
              v0 = ld_relaxed(pp);
              no = __ballot_sync(0xffffffffu, (v1 ^ bit) & 1);
              if (!(no & 0xFF)) break;
              v1 = ld_relaxed(pp);
            }
            rdy = ((1 | (no & 0xFF00 ? 0 : 2) | (no & 0xFF0000 ? 0 : 4) | (no >> 24 ? 0 : 8)) & ((1 << POLLW) - 1)) << i;
          }
          if (i >= (ph ? 2 : 4)) mbar_wait_sl(bar_done + (i + (ph ? 33 : 0)) * 8, par);
          if (el) {
            if (i == 0) PROFT(320 + l * 16 + ph * 2);
            mbar_expect_tx(bar_chk + i * 8, SLOT);
            tma_load_2d(sbase + ((slots >> (4 * i)) & 15) * SLOT, tm, bar_chk + i * 8, ((jj + i + 1) & 7) * 128 + ph * 64, row);
          }
          __syncwarp();
        }
        if (ph == 0 && el) {
          if (l) { wait_flag(&g_flags.xready[l][mm].v, ep1 * 8); fence_proxy_async_global(); }
#pragma unroll 1
          for (int u = 11; u < 34; u++) {
            if (u == 18) u = 22;
            mbar_wait_sl(bar_done + (u - 4) * 8, par);
            if (u == 32) mbar_expect_tx(bar_xr, 2 * SLOT);
            tma_load_2d(sbase + OFF_RA + (u & 3) * SLOT, tm, u < 32 ? bar_full + u * 8 : bar_xr, kslice(jj, u < 18 ? u - 2 : (u < 32 ? u - 20 : u - 32)) * 64, row);
            if (l == 0 && u < 16 && NLAYERS > 1) {
              if (u == 11) { mbar_expect_tx(bar_phi, SLOT + 8192); tma_load_2d(sbase + OFF_PHI, &tm_phi, bar_phi, 0, jj * 128); }
              else tma_load_2d(sbase + 12 * SLOT + (u - 12) * 4096, &tm_wqB, bar_phi, jj * 128 + ((u - 12) >> 1) * 64, mm * 64 + (u & 1) * 32);
            }
          }
          wait_flag(&g_flags.oready[l][mm].v, ep1 * 8);
          fence_proxy_async_global();
          PROFT(321 + l * 16);
#pragma unroll 1
          for (int s = 1; s < 5; s++) {
            if (s != 3) mbar_wait_sl(s == 2 ? bar_lx : bar_done + (s == 1 ? 30 : 31 + par) * 8, par);
            tma_load_2d(sbase + (uint32_t)((WO_ASLOT(par) >> (4 * s)) & 15) * SLOT, &tm_o, bar_full + (32 + s) * 8, wslice(jj, s) * 64, mm * 128);
          }
        }
        __syncwarp();
      }
      cluster_wait();
    } else {
      const int hw = warp - 10;
      LOAD_EPOCH();
      const bool el = elect_one();
      cluster_wait();
      if (hw == 0) {
        mbar_wait_sl(bar_full + 8, 0);
        if (lane < 7) prefetch_tmap(lane == 0 ? &tm_os : lane == 1 ? &tm_o : lane == 2 ? &tm_wf : lane == 3 ? &tm_wqB : lane == 4 ? &tm_woA : lane == 5 ? &tm_woB : &tm_phi);
        if (lane < 4) asm volatile("prefetch.global.L2 [%0];" :: "l"(prm.wB_phi + jj * 4096 + mm * 256 + lane * 64));
#pragma unroll 1
        for (int i = 0; i < 8; i++) {
          asm volatile("prefetch.global.L2 [%0];" :: "l"(prm.wB_qkv + (size_t)(mm * 64 + (i & 3) * 16 + (lane >> 1)) * 3072 + (i >> 2) * 1024 + jj * 128 + (lane & 1) * 64));
          __nanosleep(PFGAP);
        }
      } else {
#pragma unroll 1
        for (int b = 0; b < 2; b++) {
          float4* z = reinterpret_cast<float4*>(g_kv[b] + (jj * 4) * KVH + mm * (4 * KVH / 16)) + lane;
#pragma unroll
          for (int i = 0; i < 5; i++) z[i * 32] = make_float4(0.f, 0.f, 0.f, 0.f);
        }
      }
      __syncwarp();
      uint32_t chkp = 0;
#pragma unroll 1
      for (int lp = 0; lp < 2 * NLAYERS; lp++) {
        const int l = lp >> 1, ph = lp & 1;
        const uint32_t par = l & 1;
        int lane; asm volatile("mov.u32 %0, %%laneid;" : "=r"(lane));
        if (hw) {
          const uint32_t bit = ph ? O_BIT(l) : X_BIT(l - 1);
          const uint32_t slots = ph ? (uint32_t)(WO_ASLOT(par) >> 36) : 0x8769876u;
#pragma unroll 1
          for (int c = 0; c < 7; c++) {
            const uint32_t tile = sbase + ((slots >> (4 * c)) & 15) * SLOT;
#pragma unroll 1
            for (int it = 0; it < (1 << 12); it++) {
              mbar_wait_sl(bar_chk + c * 8, (chkp >> c) & 1);
              chkp ^= 1u << c;
              if (el && c == 0) PROFT(488 + lp);
              if (lp == 0) break;
              uint32_t a1 = 1, o1 = 0;
#pragma unroll
              for (int i = 0; i < 16; i++) {
                uint32_t w;
                asm volatile("ld.shared.u32 %0, [%1];" : "=r"(w) : "r"(tile + i * 1024 + (lane & 7) * 132 + (lane >> 3) * 32) : "memory");
                a1 &= w; o1 |= w;
              }
              if (__all_sync(0xffffffffu, ((bit ? a1 : ~o1) & 1) != 0)) break;
              if (el) {
                fence_proxy_async_smem();
                mbar_expect_tx(bar_chk + c * 8, SLOT);
                tma_load_2d(tile, &tm_o, bar_chk + c * 8, ((jj + c + 1) & 7) * 128 + ph * 64, mm * 128 + (ph ? 0 : S_LEN));
                RETRY_COUNT();
              }
              __syncwarp();
            }
            if (el) mbar_arrive_local(bar_full + (c + (ph ? 41 : 4)) * 8);
            __syncwarp();
          }
          if (ph) continue;
#pragma unroll 1
          for (int hp = 0; hp < 2; hp++) {
            const uint4* src = reinterpret_cast<const uint4*>(g_colsum[par][jj * 64 + hp * 32 + lane]);
            uint32_t bad;
            int it = 0;
            float c[6];
            do {
              bad = 0;
#pragma unroll
              for (int p = 0; p < 3; p++) {
                const uint4 v = ld_ll(src + ((par && p < 2) ? (hp ? -32 : 512) + p * 32 : p * 512));
                bad |= (v.y ^ ep1) | (v.w ^ ep1);
                c[2 * p] = __uint_as_float(v.x) + __uint_as_float(v.z); c[2 * p + 1] = __uint_as_float(v.y) + __uint_as_float(v.w);
              }
              bad &= 3;
              if (bad) __nanosleep(300);
            } while (bad && ++it < (1 << 16));
#pragma unroll
            for (int p = 0; p < 6; p++) {
              uint32_t h, m, lo;
              split3(c[p], h, m, lo);
              sts128(sbase + OFF_LNB + hp * 4096 + (p >> 1) * 1024 + lane * 32 + (p & 1) * 16, h | (m << 16), h | (lo << 16), h | (m << 16), lo | (m << 16));
            }
            fence_proxy_async_smem();
            __syncwarp();
            if (el) { mbar_arrive_local(hp ? bar_stat2 : bar_stat); if (hp == 0) PROFT(324 + l * 16); }
            __syncwarp();
          }
        } else if (ph == 0) {
          mbar_wait_sl(bar_done + 24, par);
          const uint4* sp = reinterpret_cast<const uint4*>(g_stats + (size_t)(mm * 128) * 8) + lane;
#pragma unroll 1
          for (int hf = 0; hf < 4; hf++) {
            uint4 v[4];
            uint32_t bad;
            int it = 0;
            do {
              bad = 0;
#pragma unroll
              for (int i = 0; i < 4; i++) { v[i] = ld_ll(sp + (hf * 4 + i) * 32); bad |= (v[i].y ^ STAT_TAG(l)) | (v[i].w ^ STAT_TAG(l)); }
              bad &= 3;
              if (bad) __nanosleep(200);
            } while (bad && ++it < (1 << 16));
            __syncwarp();
            float mean = 0.f, m2 = 0.f;
#pragma unroll
            for (int i = 0; i < 4; i++) {
              float a = __uint_as_float(v[i].x) + __uint_as_float(v[i].z);
              a += __shfl_xor_sync(0xffffffffu, a, 1); a += __shfl_xor_sync(0xffffffffu, a, 2);
              a *= 0.125f;
              const float e0 = __uint_as_float(v[i].x) - a, e1 = __uint_as_float(v[i].z) - a;
              float q = fmaf(fmaf(e0, e0, e1 * e1), 128.f, __uint_as_float(v[i].y) + __uint_as_float(v[i].w));
              q += __shfl_xor_sync(0xffffffffu, q, 1); q += __shfl_xor_sync(0xffffffffu, q, 2);
              if ((lane & 3) == i) { mean = a; m2 = q; }
            }
            const uint32_t row = hf * 32 + (lane & 3) * 8 + (lane >> 2);
            uint32_t h, m, lo;
            split3(-0.5f * mean, h, m, lo);
            sts128(sbase + OFF_LNA + row * 16, h | (h << 16), m | (h << 16), lo | (m << 16), m | (lo << 16));
            sts32f(sbase + OFF_ST + row * 4, rsqrtf(m2 * (1.f / 1024.f) + 1e-5f));
          }
          fence_proxy_async_smem();
          __syncwarp();
          if (el) { mbar_arrive_local(bar_stat); PROFT(323 + l * 16); }
          __syncwarp();
#pragma unroll 1
          for (int i = 0; i < 8 - 4 * l; i++) {
            asm volatile("prefetch.global.L2 [%0];" :: "l"(i < 4 ? (l ? prm.wB_o : prm.wA_o) + (size_t)cta * 8192 + i * 2048 + lane * 64
                                                                 : prm.wB_qkv + (size_t)(cta * 8 + (i - 4) * 2 + (lane >> 4)) * 3072 + 2048 + (lane & 15) * 64));
            __nanosleep(PFGAP);
          }
          continue;
        }
        if (hw) {
          if (l & 1) {
#pragma unroll 1
            for (int h = 0; h < 2; h++) {
              asm volatile("bar.sync %0, 288;" :: "r"(BAR_KV + h) : "memory");
              __syncwarp();
              PROFT(331 + l * 16 + h);
              if (lane < 16) signal_release(&g_flags.kvready[(l & 2) + h][jj][lane].v);
              const unsigned* kf = &g_flags.kvready[(l & 2) + h][jj][mm].v;
              unsigned v0 = ld_relaxed(kf);
              __nanosleep(150);
              unsigned v1 = ld_relaxed(kf);
#pragma unroll 1
              for (int it = 0; it < (1 << 18); it++) {
                if (v0 == ep1 * 16) break;
                v0 = ld_relaxed(kf);
                if (v1 == ep1 * 16) break;
                v1 = ld_relaxed(kf);
              }
              fence_acquire();
              __syncwarp();
              if (el) { mbar_arrive_local(bar_kvf + h * 8); PROFT(333 + l * 16 + h); }
              __syncwarp();
            }
          }
        } else {
#pragma unroll 1
          for (uint32_t ev = l == NLAYERS - 1 ? 0x80u : (l == 0 ? 0x836054u : 0x830u); ev != 8; ev >>= 4) {
            const int e = ev & 15;
            asm volatile("bar.sync %0, 288;" :: "r"((0xFECA987 >> (4 * e)) & 15) : "memory");
            if (el) {
              if (e < 4) {
                PROFT(325 + l * 16 + e);
                tma_store_2d(&tm_o, sbase + (e ? 11 : 12) * SLOT, jj * 128 + (e & 1) * 64, mm * 128 + (e ? S_LEN : 0));
              } else {
                if (e == 5) mbar_expect_tx(bar_phi + 8, SLOT);
#pragma unroll 1
                for (int i = 0; i < 4; i++) {
                  const uint32_t a = sbase + (e > 4 ? 10 : 12) * SLOT + i * 4096;
                  const int c0 = (e > 4 ? 1024 : 0) + jj * 128 + (i >> 1) * 64, c1 = mm * 64 + (i & 1) * 32;
                  if (e == 5) tma_load_2d(a, &tm_wqB, bar_phi + 8, c0, c1); else tma_store_2d(&tm_wf, a, c0, c1);
                }
                if (e != 5) {
                  asm volatile("cp.async.bulk.commit_group;\ncp.async.bulk.wait_group.read 0;" ::: "memory");
                  mbar_arrive_local(bar_phi + (e - 4) * 4);
                }
              }
              if ((0x49 >> e) & 1) {
                bulk_commit_wait();
                signal_release(e == 0 ? &g_flags.oready[l][mm].v : e == 6 ? &g_flags.wfready[jj].v : &g_flags.xready[l + 1][mm].v);
              }
              if (e == 3) PROFT(330 + l * 16);
              if (e == 6) PROFT(335);
            }
            __syncwarp();
          }
        }
      }
    }
    cluster_sync();
  } else {
    asm volatile("setmaxnreg.inc.sync.aligned.u32 232;");
    LOAD_EPOCH();
    const int wg = warp >> 2;
    const int r0 = warp * 16;
    const uint32_t pK = sbase + OFF_S, pV = sbase + OFF_S + SLOT;
#define PMASKS(on, bit) const uint32_t pm0 = ((on) && t == (g & 3) && (g >> 2) == (g & 1)), pm1 = ((on) && t == (g & 3) && (g >> 2) != (g & 1)), pbit = (bit)
#define PBIT0(w) (((w) & ~pm0) | (pbit & pm0))
#define PBIT1(w) (((w) & ~pm1) | (pbit & pm1))
#define LANE_CONSTS() \
    int lane; asm volatile("mov.u32 %0, %%laneid;" : "=r"(lane)); \
    const int g = lane >> 2, t = lane & 3; \
    const uint32_t srowoff = (r0 + (lane & 15)) * 128, lsw = (lane & 7) << 4, lhi = (lane >> 4) << 4, lsw2 = (lane & 6) << 3; \
    (void)g; (void)t; (void)srowoff; (void)lsw; (void)lhi; (void)lsw2;
    uint32_t stgp = 0, peer;
    asm volatile("mapa.shared::cluster.u32 %0, %1, %2;" : "=r"(peer) : "r"(sbase), "r"(rank ^ 1));
    peer -= sbase;
    const uint32_t dA0 = (((sbase & 0x3FFFF) + wg * 8192) >> 4) | 0x10000u, dB0 = ((sbase & 0x3FFFF) >> 4) | 0x2000000u;
    cluster_wait();
#define STG_ARRIVE() { __syncwarp(); if (elect_one()) mbar_arrive_local(bar_stg); }
#define STG_WAIT() { mbar_wait(bar_stg, stgp); stgp ^= 1; }
#define PROFS() do {} while (0)
#define REL(addr) { if (elect_one()) { mbar_arrive_local(addr); asm volatile("mbarrier.arrive.shared::cluster.b64 _, [%0];" :: "r"((addr) + peer) : "memory"); } }
#define QSTEP(ACC, DA, SC, PRE) { \
      const uint32_t da = (DA), db = dB0 + (ub & 0x18) * (QST >> 7); \
      mbar_wait(ub, par); \
      PRE; \
      wgmma_fence(); \
      wgmma4_n192<SC>(ACC, da, db); \
      wgmma_commit(); PROFS(); }
#define QREL() { wgmma_wait<1>(); REL(ub + 376); ub += 8; }
#define RA_CUR (dA0 + (OFF_RA >> 4) + (ub & 0x18) * (SLOT >> 7))
#define PUMP1() { QSTEP(S1, RA_CUR, 1, {}); QREL(); }
#define PUMP0() { PUMP1(); SCHED_FENCE(); }
#define PUMP() if (h == 0) PUMP1()
#define WSTEP() { \
      const uint32_t s4 = (ub - bar_full - 256) >> 1; \
      const uint32_t da = dA0 + (((uint32_t)(WO_ASLOT(par) >> s4) & 15) << 10), db = dB0 + (((uint32_t)(WO_BSLOT >> s4) & 15) << 10); \
      mbar_wait(ub, par); \
      wgmma_fence(); \
      wgmma4_n128<1>(S1, da, db); \
      wgmma_commit(); PROFS(); \
      wgmma_wait<1>(); \
      if (s4 > par * 4) REL(ub + 376); \
      ub += 8; }
#define PUMPS(n) { _Pragma("unroll 1") for (int i_ = 0; i_ < (n); i_++) PUMP1(); }
#define SITE(n) { if ((BMASK >> (n)) & 1) PUMP1(); SCHED_FENCE(); }
#define LNSTEP(ACC, hh) { wgmma_fence(); wgmma_n192<1, 0>(ACC, make_desc(sbase + OFF_LNA + wg * 1024, 0, 128) ^ (1ull << 62), make_desc(sbase + OFF_LNB + (hh) * 4096, 0, 128) ^ (1ull << 62)); }
#define DRAIN_A(ACC, PMP) { \
      LANE_CONSTS(); \
      STAGE64(ACC, 64, pV, 1, 1); \
      PMP; \
      STAGE64(ACC, 32, pK, 0, 1); \
      STG_ARRIVE(); \
      _Pragma("unroll") for (int i_ = 0; i_ < 16; i_++) qa[i_] = pack_bf16(ACC[2 * i_], ACC[2 * i_ + 1]); \
      PINU(qa, 16); }
#define DRAIN_B(ACC) { \
      LANE_CONSTS(); \
      STAGE64(ACC, 64, pV, 1, 0); \
      _Pragma("unroll") for (int i_ = 0; i_ < 64; i_++) st[i_] = ACC[i_]; \
      PIN(st, 64); }
#define WARP_STORE(tm, tile, col, row) { fence_proxy_async_smem(); __syncwarp(); \
      if (elect_one()) { tma_store_2d(tm, (tile) + r0 * 128, col, (row) + r0); asm volatile("cp.async.bulk.commit_group;" ::: "memory"); } __syncwarp(); }
#define PUBLISH_O() { if (h) WARP_STORE(&tm_os, pO, jj * 128 + 64, mm * 128) else { fence_proxy_async_smem(); bar_arrive<BAR_O, 288>(); } }
#define X_OUT(pc, on) { \
      PMASKS(on, X_BIT(l)); \
      _Pragma("unroll") for (int j = (pc) * 4; j < (pc) * 4 + 4; j++) \
        stsm_x4(pK + (pc) * SLOT + srowoff + ((((uint32_t)(j & 3) << 5) + lhi) ^ lsw), \
                PBIT0(pack_bf16(S1[j * 8 + 0], S1[j * 8 + 1])), PBIT0(pack_bf16(S1[j * 8 + 2], S1[j * 8 + 3])), \
                PBIT1(pack_bf16(S1[j * 8 + 4], S1[j * 8 + 5])), PBIT1(pack_bf16(S1[j * 8 + 6], S1[j * 8 + 7]))); }
#define REST_P1(SKEW) { \
      mbar_wait(bar_stat2, par); \
      LNSTEP(S1, 1); \
      _Pragma("unroll 1") while (ub < bar_full + 256) { \
        if (ub == bar_full + 256 - 8 * (SKEW) && wg == 0) bar_sync<BAR_SKEW, 256>(); \
        QSTEP(S1, RA_CUR, 1, {}); \
        if (ub == bar_full + 248 && wg == 1) bar_arrive<BAR_SKEW, 256>(); \
        QREL(); \
      } \
      hbase += 256; \
      mbar_wait(bar_done + (31 - (SKEW)) * 8, par);        \
      wgmma_wait<0>(); \
      ACC_FENCE(S1, 96); \
      REL(bar_done + 31 * 8); \
      PROF(13); }
#define FOLD(tile, rd) { \
          LANE_CONSTS(); \
          float d[32]; \
          ACC_DEF(d, 32); \
          mbar_wait(bar_phi + (rd) * 8, 0); \
          wgmma_fence(); \
          _Pragma("unroll") for (int i = 0; i < 2; i++) { \
            const uint64_t da = make_desc((tile) + wg * 8192 + i * 64, 16, 1024); \
            const uint64_t db = make_desc(sbase + OFF_PHI + wg * 4096 + i * 2048, 16, 512) ^ (3ull << 62); \
            wgmma_n32<0>(d + i * 16, da, db); wgmma_n32<1>(d + i * 16, da + 2, db + 64); \
          } \
          wgmma_commit(); \
          PUMP0(); \
          ACC_FENCE(d, 32); \
          bar_wg(wg); \
          _Pragma("unroll") for (int i = 0; i < 4; i++) { \
            const float* x = d + (i & 1) * 8 + (i >> 1) * 2; \
            sts128((tile) + wg * 8192 + ((warp & 3) * 16 + (i >> 1) * 8 + g) * 128 + (((2 * t + (i & 1)) ^ g) << 4), \
                   pack_bf16(x[0], x[1]), pack_bf16(x[4], x[5]), pack_bf16(x[16], x[17]), pack_bf16(x[20], x[21])); \
          } \
          fence_proxy_async_smem(); \
          bar_arrive<BAR_WF + 3 * (rd), 288>(); }
#define LOAD_X0(base) \
      _Pragma("unroll") for (int j = 0; j < 8; j++) { \
        uint32_t x0, x1, x2, x3; \
        ldsm_x4((base) + (j >> 2) * SLOT + srowoff + ((((uint32_t)(j & 3) << 5) + lhi) ^ lsw), x0, x1, x2, x3); \
        S1[j * 8 + 0] = bf_lo(x0); S1[j * 8 + 1] = bf_hi(x0); S1[j * 8 + 2] = bf_lo(x1); S1[j * 8 + 3] = bf_hi(x1); \
        S1[j * 8 + 4] = bf_lo(x2); S1[j * 8 + 5] = bf_hi(x2); S1[j * 8 + 6] = bf_lo(x3); S1[j * 8 + 7] = bf_hi(x3); \
      }
#define LOAD_X() { \
      wgmma_wait<0>(); \
      mbar_wait(bar_xr, par); \
      LOAD_X0(sbase + OFF_RA); \
      ACC_FENCE(S1, 64); \
      __syncwarp(); if (elect_one()) mbar_arrive_local(bar_lx); }

    float S1[96];
#pragma unroll
    for (int i = 0; i < 64; i++) S1[i] = 0.f;
#pragma unroll 1
    for (int l = 0; l < NLAYERS; l++) {
      const uint32_t par = l & 1;
      bar_wg(wg);
      PROF(0);
      uint32_t ub = bar_full;
      const bool hsend = (warp == 7) && (mm < 15);
      const uint32_t hbit = (NLAYERS > 2) ? (l == 0) : (ep1 & 1);
      float S0[96];
      {
        LANE_CONSTS();
        ACC_DEF(S0, 96);
        QSTEP(S0, dA0 + (OFF_S >> 4), 0, {});
        ub += 8;
        PROF(1);
        if (l == 0) { mbar_wait(ub, 0); LOAD_X0(pK); }
        else { X_OUT(1, false); fence_proxy_async_smem(); }
        SCHED_FENCE();
        {
          float a0 = S1[0], a1 = S1[2], b0 = S1[1], b1 = S1[3];
#pragma unroll
          for (int i = 4; i < 64; i += 4) { a0 += S1[i]; b0 += S1[i + 1]; a1 += S1[i + 2]; b1 += S1[i + 3]; }
          a0 += b0; a1 += b1;
          a0 += __shfl_xor_sync(0xffffffffu, a0, 1); a1 += __shfl_xor_sync(0xffffffffu, a1, 1);
          a0 += __shfl_xor_sync(0xffffffffu, a0, 2); a1 += __shfl_xor_sync(0xffffffffu, a1, 2);
          a0 *= (1.f / 128.f); a1 *= (1.f / 128.f);
          asm volatile("" : "+f"(a0), "+f"(a1));
          bar_wg(wg);
          QSTEP(S0, dA0 + ((OFF_S + SLOT) >> 4), 1, wgmma_wait<0>());
          REL(ub + 376); ub += 8;
          SCHED_FENCE();
          float q0 = 0.f, q1 = 0.f;
          b0 = 0.f; b1 = 0.f;
#pragma unroll
          for (int i = 0; i < 64; i += 4) {
            const float d0 = S1[i] - a0, d1 = S1[i + 1] - a0, d2 = S1[i + 2] - a1, d3 = S1[i + 3] - a1;
            q0 = fmaf(d0, d0, q0); b0 = fmaf(d1, d1, b0); q1 = fmaf(d2, d2, q1); b1 = fmaf(d3, d3, b1);
          }
          q0 += b0; q1 += b1;
          q0 += __shfl_xor_sync(0xffffffffu, q0, 1); q1 += __shfl_xor_sync(0xffffffffu, q1, 1);
          q0 += __shfl_xor_sync(0xffffffffu, q0, 2); q1 += __shfl_xor_sync(0xffffffffu, q1, 2);
          if (t < 2) st_b64(g_stats + (size_t)(mm * 128 + r0 + g + t * 8) * 8 + jj, __float_as_uint(t ? a1 : a0), (__float_as_uint(t ? q1 : q0) & ~3u) | STAT_TAG(l));
        }
        if (l) { asm volatile("cp.async.bulk.wait_group 0;" ::: "memory"); bar_arrive<BAR_O + 3, 288>(); }
        ACC_DEF(S1, 96);
        QSTEP(S1, dA0 + (OFF_S >> 4), 0, {});
        QREL();
        QSTEP(S1, dA0 + ((OFF_S + SLOT) >> 4), 1, {});
        QREL();
#pragma unroll 1
        for (int i = 0; i < 14; i++) {
          QSTEP(S0, RA_CUR, 1, {});
          if (i == 0) PROF(2);
          QREL();
        }
      }
      LANE_CONSTS();
      uint4* hbase = g_halo + (size_t)(mm * 8 + jj) * 512;
      mbar_wait(bar_stat, par);
      LNSTEP(S0, 0);
      wgmma_commit();
      const float rs0 = lds32f(sbase + OFF_ST + (r0 + g) * 4), rs1 = lds32f(sbase + OFF_ST + (r0 + g + 8) * 4);
      PUMP0();
      ACC_FENCE(S0, 96);
      PROF(3);
      if (!par) {
        constexpr uint32_t par = 0;
        uint32_t qa[16];
        DRAIN_A(S0, PUMP0());
#pragma unroll 1
        for (int h = 0; h < 2; h++) {
          const uint32_t pO = sbase + (h ? 3 : 12) * SLOT;
          PROF(4 + h * 12);
          const bool fold = (l == 0 && h == 0 && NLAYERS > 1);
          if (fold) FOLD(pO, 0) else if (h == 0) PUMPS(HPUMP1);
          LANE_CONSTS();
          uint4 hv[8];
#pragma unroll
          for (int i = 0; i < 8; i++) hv[i] = make_uint4(hbit, 0, 0, 0);
          const bool hrec = (warp == 0 && mm > 0);
          if (hrec) {
#pragma unroll
            for (int i = 0; i < 8; i++) hv[i] = ld_b128(hbase + lane - 8 * 512 + i * 32);
          }
          if (h) LOAD_X() else PUMPS(HPUMP2);
          const uint32_t halo = sbase + OFF_HALO;
          STG_WAIT();
          if (warp == 0) {
#pragma unroll 1
            for (int it = 0; it < (1 << 16); it++) {
              uint32_t bad = 0;
#pragma unroll
              for (int i = 0; i < 8; i++) bad |= hv[i].x ^ hbit;
              if (__all_sync(0xffffffffu, (bad & 1) == 0)) break;
#pragma unroll
              for (int i = 0; i < 8; i++) hv[i] = ld_b128(hbase + lane - 8 * 512 + i * 32);
            }
#pragma unroll
            for (int i = 0; i < 8; i++)
              stsm_x4(i < 4 ? halo + srowoff + ((((uint32_t)i << 5) + lhi) ^ lsw)
                            : halo + (srowoff >> 1) + (i >> 1) * 1024 + ((((uint32_t)(i & 1) << 5) + lhi) ^ lsw2), hv[i].x, hv[i].y, hv[i].z, hv[i].w);
            __syncwarp();
          }
          PROF(5 + h * 12);
          const uint32_t kb1 = pK + r0 * 128, vb1 = pV + r0 * 64;
          const uint32_t kb0 = r0 ? kb1 - 2048 : halo, vb0 = r0 ? vb1 - 1024 : halo + 2048;
          const uint32_t vhs = r0 ? 8192 : 1024;
          float s[2][4][4];
          {
            uint32_t kf[2][4][4];
#pragma unroll
            for (int i = 0; i < 8; i++) {
              const int hh = i >> 2, jb = i & 3;
              ldsm_x4(((jb < 2) ? kb0 : kb1) + ((jb & 1) * 8 + (lane & 7)) * 128 + ((hh * 64 + ((lane >> 3) << 4)) ^ lsw), kf[hh][jb][0], kf[hh][jb][1], kf[hh][jb][2], kf[hh][jb][3]);
              s[hh][jb][0] = s[hh][jb][1] = s[hh][jb][2] = s[hh][jb][3] = 0.f;
            }
#pragma unroll
            for (int ks = 0; ks < 2; ks++)
#pragma unroll
              for (int i = 0; i < 8; i++) {
                const int hh = i >> 2, jb = i & 3;
                mma_bf16(s[hh][jb], qa[hh * 8 + ks * 4], qa[hh * 8 + ks * 4 + 1], qa[hh * 8 + ks * 4 + 2], qa[hh * 8 + ks * 4 + 3], kf[hh][jb][ks * 2], kf[hh][jb][ks * 2 + 1]);
              }
          }
          PUMP();
          if (fold) bar_arrive<BAR_WF + 2, 288>();
          PROF(6 + h * 12);
          const bool e = g & 1, hb = (2 * t + (g & 1)) <= g;
          uint32_t vf[2][2][2][4];
#pragma unroll
          for (int i = 0; i < 8; i++) {
            const int hh = i >> 2, ks = (i >> 1) & 1, dp = i & 1;
            ldsm_x4_t((ks ? vb1 + hh * 8192 : vb0 + hh * vhs) + (lane & 15) * 64 + ((dp * 32 + lhi) ^ lsw2), vf[hh][ks][dp][0], vf[hh][ks][dp][1], vf[hh][ks][dp][2], vf[hh][ks][dp][3]);
          }
          float va[2][2], vb[2][2], mx[2][2];
#pragma unroll
          for (int hh = 0; hh < 2; hh++) {
            va[hh][0] = e ? s[hh][1][1] : s[hh][1][0];
            vb[hh][0] = hb ? (e ? s[hh][2][1] : s[hh][2][0]) : (e ? s[hh][0][1] : s[hh][0][0]);
            va[hh][1] = e ? s[hh][2][3] : s[hh][2][2];
            vb[hh][1] = hb ? (e ? s[hh][3][3] : s[hh][3][2]) : (e ? s[hh][1][3] : s[hh][1][2]);
          }
          if (warp == 0 && mm == 0) {
#pragma unroll
            for (int hh = 0; hh < 2; hh++) { va[hh][0] = -INFINITY; if (!hb) { vb[hh][0] = -INFINITY; vb[hh][1] = -INFINITY; } }
          }
#pragma unroll
          for (int i = 0; i < 4; i++) mx[i >> 1][i & 1] = fmaxf(va[i >> 1][i & 1], vb[i >> 1][i & 1]);
#pragma unroll
          for (int o = 1; o <= 2; o <<= 1)
#pragma unroll
            for (int i = 0; i < 4; i++) mx[i >> 1][i & 1] = fmaxf(mx[i >> 1][i & 1], __shfl_xor_sync(0xffffffffu, mx[i >> 1][i & 1], o));
          const float sc0 = rs0 * (0.17677669529663687f * LOG2E), sc1 = rs1 * (0.17677669529663687f * LOG2E);
#pragma unroll
          for (int i = 0; i < 4; i++) {
            const float sc = (i & 1) ? sc1 : sc0, m = mx[i >> 1][i & 1];
            va[i >> 1][i & 1] = ex2((va[i >> 1][i & 1] - m) * sc); vb[i >> 1][i & 1] = ex2((vb[i >> 1][i & 1] - m) * sc);
            mx[i >> 1][i & 1] = va[i >> 1][i & 1] + vb[i >> 1][i & 1];
          }
          if (h == 0 && ASITE) { PIN(&va[0][0], 4); PIN(&vb[0][0], 4); PIN(&mx[0][0], 4); PUMP1(); }
#pragma unroll
          for (int o = 1; o <= 2; o <<= 1)
#pragma unroll
            for (int i = 0; i < 4; i++) mx[i >> 1][i & 1] += __shfl_xor_sync(0xffffffffu, mx[i >> 1][i & 1], o);
          const uint32_t selA = e ? 0x1044 : 0x4410, selB = e ? 0x3244 : 0x4432, selL = hb ? 0x4444 : selB, selH = hb ? selB : 0x4444;
          float o[2][4][4];
          uint32_t pa[2][6];
#pragma unroll
          for (int hh = 0; hh < 2; hh++) {
            const float i0 = rcp_fast(mx[hh][0]), i1 = rcp_fast(mx[hh][1]);
            const uint32_t w0 = pack_bf16(va[hh][0] * i0, vb[hh][0] * i0), w1 = pack_bf16(va[hh][1] * i1, vb[hh][1] * i1);
            pa[hh][0] = __byte_perm(w0, 0, selL); pa[hh][1] = __byte_perm(w0, 0, selA); pa[hh][2] = __byte_perm(w1, 0, selL);
            pa[hh][3] = __byte_perm(w0, 0, selH); pa[hh][4] = __byte_perm(w1, 0, selA); pa[hh][5] = __byte_perm(w1, 0, selH);
#pragma unroll
            for (int dj = 0; dj < 4; dj++) { o[hh][dj][0] = o[hh][dj][1] = o[hh][dj][2] = o[hh][dj][3] = 0.f; }
          }
          PROF(7 + h * 12);
#pragma unroll
          for (int i = 0; i < 8; i++) mma_bf16(o[i >> 2][i & 3], pa[i >> 2][0], 0u, pa[i >> 2][1], pa[i >> 2][2], vf[i >> 2][0][(i >> 1) & 1][(i & 1) * 2], vf[i >> 2][0][(i >> 1) & 1][(i & 1) * 2 + 1]);
#pragma unroll
          for (int i = 0; i < 8; i++) mma_bf16(o[i >> 2][i & 3], pa[i >> 2][3], pa[i >> 2][4], 0u, pa[i >> 2][5], vf[i >> 2][1][(i >> 1) & 1][(i & 1) * 2], vf[i >> 2][1][(i >> 1) & 1][(i & 1) * 2 + 1]);
          if (h == 0) PUMP1() else mbar_wait(bar_done + 30 * 8, par);
          if (fold) mbar_wait(bar_phi, 1);
#pragma unroll
          for (int i = 0; i < 4; i++) {
            const int hh = i >> 1, dp = i & 1;
            PMASKS(h, O_BIT(l));
            stsm_x4(pO + srowoff + ((hh * 64 + dp * 32 + lhi) ^ lsw), PBIT0(pack_bf16(o[hh][dp * 2][0], o[hh][dp * 2][1])), PBIT0(pack_bf16(o[hh][dp * 2][2], o[hh][dp * 2][3])),
                    PBIT1(pack_bf16(o[hh][dp * 2 + 1][0], o[hh][dp * 2 + 1][1])), PBIT1(pack_bf16(o[hh][dp * 2 + 1][2], o[hh][dp * 2 + 1][3])));
          }
          PUBLISH_O();
          PROF(11 + h * 12);
          if (h) break;
          if (fold) { PUMPS(FPUMP); FOLD(pK, 1); }
          REST_P1(ASKEW);
          if (fold) mbar_wait(bar_phi + 8, 1);
          DRAIN_A(S1, {});
        }
      } else {
        constexpr uint32_t par = 1;
        float st[64];
        DRAIN_B(S0);
        if (warp < 2) sts128(sbase + OFF_ONES + warp * 512 + lane * 16, 0x3F803F80u, 0x3F803F80u, 0x3F803F80u, 0x3F803F80u);
        const float c0 = rs0 * LOG2E, c1 = rs1 * LOG2E;
#define KV_PART(hp, ...) { \
          float kv[20]; \
          ACC_DEF(kv, 20); \
          const uint64_t dp = make_desc(wg ? pK : sbase + 12 * SLOT, 16, 1024); \
          const uint64_t dv = (make_desc(pV + wg * 8192, OFF_ONES - OFF_S - SLOT - wg * 8192, 512) ^ (3ull << 62)); \
          constexpr uint64_t DVS = 64ull - (64ull << 16); \
          fence_proxy_async_smem(); \
          STG_ARRIVE(); \
          STG_WAIT(); \
          wgmma_fence(); \
          _Pragma("unroll") for (int ks = 0; ks < 8; ks++) { if (ks == 0) wgmma_n40<0, 1>(kv, dp, dv); else wgmma_n40<1, 1>(kv, dp + ks * 128, dv + ks * DVS); } \
          wgmma_commit(); \
          __VA_ARGS__; \
          ACC_FENCE(kv, 20); \
          float* kvg = g_kv[l >> 1] + (jj * 4 + (hp) * 2 + wg) * KVH + ((warp & 3) * 32 + lane) * 4; \
          _Pragma("unroll") for (int i = 0; i < 4; i++) red_v4(kvg + i * 512, kv[i * 4], kv[i * 4 + 1], kv[i * 4 + 2], kv[i * 4 + 3]); \
          if (t == 0) red_v4(kvg + 2048, kv[16], kv[17], kv[18], kv[19]); \
          bar_arrive<BAR_KV + (hp), 288>(); \
          STG_ARRIVE(); }
#pragma unroll 1
        for (int h = 0; h < 2; h++) {
          PROF(4 + h * 2);
          SITE(0);
          LANE_CONSTS();
          const uint32_t dsw = (uint32_t)(g ^ (2 * t)) << 4, dst = ((t & 2) ? pK : sbase + 12 * SLOT) + (r0 + g) * 128;
          float e[16], f[16];
          float mn0 = rmin16(st);
          asm volatile("" : "+f"(mn0)); SCHED_FENCE();
          float sa = exps16(e, st, -c0, mn0 * c0), mx0 = rmax16(st);
          asm volatile("" : "+f"(sa), "+f"(mx0)); PIN(e, 16); SITE(1);
          if (h) STG_WAIT();
          store16(e, sa, dst, dsw, 4);
          float sb = exps16(f, st, c0, -mx0 * c0), mn1 = rmin16(st + 2);
          asm volatile("" : "+f"(sb), "+f"(mn1)); PIN(f, 16); SITE(2);
          store16(f, sb, dst, dsw, 0);
          float sc = exps16(e, st + 2, -c1, mn1 * c1), mx1 = rmax16(st + 2);
          asm volatile("" : "+f"(sc), "+f"(mx1)); PIN(e, 16); SITE(3);
          store16(e, sc, dst + 1024, dsw, 4);
          float sd = exps16(f, st + 2, c1, -mx1 * c1);
          asm volatile("" : "+f"(sd)); PIN(f, 16); SITE(4);
          store16(f, sd, dst + 1024, dsw, 0);
          PROF(5 + h * 2);
          if (h) break;
          KV_PART(0, PUMP0());
#pragma unroll
          for (int i = 0; i < 32; i++) st[i] = st[32 + i];
        }
        REST_P1(1);
        float mq[4];
#define EXTREMA(p) { mq[0] = rmin16(p) * c0; mq[1] = rmax16(p) * -c0; mq[2] = rmin16((p) + 2) * c1; mq[3] = rmax16((p) + 2) * -c1; PIN(mq, 4); }
        {
          LANE_CONSTS();
          DRAIN_B(S1);
          PROF(16);
          KV_PART(1, { SCHED_FENCE(); EXTREMA(st); wgmma_wait<0>(); });
          PROF(17);
        }
#pragma unroll 1
        for (int h = 0; h < 2; h++) {
          const uint32_t pO = sbase + (h ? 3 : 12) * SLOT, pP = sbase + (h ? 9 : 10) * SLOT, pT = sbase + (h ? 11 : 8) * SLOT;
          LANE_CONSTS();
          const float4* kvg = reinterpret_cast<const float4*>(g_kv[l >> 1] + (jj * 4 + h * 2 + wg) * KVH) + (warp & 3) * 32 + lane;
          float4 v[5];
          mbar_wait(bar_kvf + h * 8, l >> 1);
          PROF(25 + h);
#pragma unroll
          for (int i = 0; i < 4; i++) v[i] = __ldcg(kvg + i * 128);
          v[4] = __ldcg(kvg + 512 - t);
          const uint32_t dsw = (uint32_t)(g ^ (2 * t)) << 4, dst = ((t & 2) ? pP : pO) + (r0 + g) * 128;
          uint32_t fq[16];
          expp16(fq, st, -c0, mq[0]);
          expp16(fq + 8, st, c0, mq[1]);
          PINU(fq, 16);
          if (h == 0) STG_WAIT();
#pragma unroll
          for (int i = 0; i < 4; i++) sts128(dst + (((((i & 2) ? 0 : 4) + (i & 1)) << 4) ^ dsw), fq[i * 4], fq[i * 4 + 1], fq[i * 4 + 2], fq[i * 4 + 3]);
          expp16(fq, st + 2, -c1, mq[2]);
          expp16(fq + 8, st + 2, c1, mq[3]);
#pragma unroll
          for (int i = 0; i < 4; i++) sts128(dst + 1024 + (((((i & 2) ? 0 : 4) + (i & 1)) << 4) ^ dsw), fq[i * 4], fq[i * 4 + 1], fq[i * 4 + 2], fq[i * 4 + 3]);
          PROF(18 + h * 14);
          if (h) {
            wgmma_wait<0>();
            REL(bar_done + 32 * 8);
          }
          {
            const uint32_t kd = pT + wg * 8192 + ((warp & 3) * 16 + (lane & 15)) * 128;
#pragma unroll
            for (int i = 0; i < 2; i++) {
              const float4 a = v[i * 2], b = v[i * 2 + 1];
              stsm_x4(kd + ((i * 32 + lhi) ^ lsw), pack_bf16(a.x, a.y), pack_bf16(a.z, a.w), pack_bf16(b.x, b.y), pack_bf16(b.z, b.w));
            }
            stsm_x4(kd + ((64u + lhi) ^ lsw), pack_bf16(v[4].x, 1.f), pack_bf16(v[4].z, 1.f), 0u, 0u);
          }
          fence_proxy_async_smem();
          STG_ARRIVE();
          float o[4][20];
          ACC_DEF(o[0], 20); ACC_DEF(o[1], 20); ACC_DEF(o[2], 20); ACC_DEF(o[3], 20);
          STG_WAIT();
          PROF(19 + h * 14);
          wgmma_fence();
#pragma unroll
          for (int hh = 0; hh < 2; hh++) {
            const uint64_t da = make_desc((hh ? pP : pO) + wg * 8192, 16, 1024);
            const uint64_t db = make_desc(pT + hh * 8192, 16, 1024);
#pragma unroll
            for (int ks = 0; ks < 4; ks += 2) { wgmma_n40<0, 0>(o[hh * 2 + (ks >> 1)], da + ks * 2, db + ks * 128); wgmma_n40<1, 0>(o[hh * 2 + (ks >> 1)], da + ks * 2 + 2, db + ks * 128 + 128); }
          }
          wgmma_commit();
          if (h == 0) EXTREMA(st + 32);
          wgmma_wait<0>();
          ACC_FENCE(o[0], 20); ACC_FENCE(o[1], 20); ACC_FENCE(o[2], 20); ACC_FENCE(o[3], 20);
          bar_wg(wg);
          PMASKS(h, O_BIT(l));
#pragma unroll
          for (int hh = 0; hh < 2; hh++) {
            const float* x = o[hh * 2];
            const float* y = o[hh * 2 + 1];
            const float rx0 = rcp_fast(x[17]), ry0 = rcp_fast(y[17]), rx1 = rcp_fast(x[19]), ry1 = rcp_fast(y[19]);
            const float i0 = rcp_fast(fmaf(x[16], rx0, y[16] * ry0) + 1e-6f), i1 = rcp_fast(fmaf(x[18], rx1, y[18] * ry1) + 1e-6f);
            const float ax0 = rx0 * i0, ay0 = ry0 * i0, ax1 = rx1 * i1, ay1 = ry1 * i1;
#pragma unroll
            for (int dp = 0; dp < 2; dp++)
              stsm_x4(pO + srowoff + ((hh * 64 + dp * 32 + lhi) ^ lsw),
                      PBIT0(pack_bf16(fmaf(x[dp * 8], ax0, y[dp * 8] * ay0), fmaf(x[dp * 8 + 1], ax0, y[dp * 8 + 1] * ay0))),
                      PBIT0(pack_bf16(fmaf(x[dp * 8 + 2], ax1, y[dp * 8 + 2] * ay1), fmaf(x[dp * 8 + 3], ax1, y[dp * 8 + 3] * ay1))),
                      PBIT1(pack_bf16(fmaf(x[dp * 8 + 4], ax0, y[dp * 8 + 4] * ay0), fmaf(x[dp * 8 + 5], ax0, y[dp * 8 + 5] * ay0))),
                      PBIT1(pack_bf16(fmaf(x[dp * 8 + 6], ax1, y[dp * 8 + 6] * ay1), fmaf(x[dp * 8 + 7], ax1, y[dp * 8 + 7] * ay1))));
          }
          PUBLISH_O();
          PROF(20 + h * 14);
          if (h) break;
          LOAD_X();
          bar_wg(wg);
          WSTEP();
#pragma unroll
          for (int i = 0; i < 32; i++) st[i] = st[32 + i];
        }
      }
      __syncwarp();
      if (elect_one()) mbar_arrive_local(bar_epi);
      bar_wg(wg);
#pragma unroll 1
      while (ub < bar_full + 384) {
        WSTEP();
        if (ub == bar_full + 8 * 41) { asm volatile("cp.async.bulk.wait_group.read 0;" ::: "memory"); PROF(35); }
        if (ub == bar_full + 8 * 42) PROF(36);
      }
      wgmma_wait<0>();
      ACC_FENCE(S1, 64);
      REL(bar_done + 47 * 8);
      PROF(37);
      {
        LANE_CONSTS();
        X_OUT(0, l < NLAYERS - 1);
        WARP_STORE(l < NLAYERS - 1 ? &tm_os : &tm_xo, pK, jj * 128, mm * 128 + (l < NLAYERS - 1 ? S_LEN : 0));
        if (l == NLAYERS - 1) {
          X_OUT(1, false);
          WARP_STORE(&tm_xo, pV, jj * 128 + 64, mm * 128);
          asm volatile("cp.async.bulk.wait_group 0;" ::: "memory");
        }
      }
#pragma unroll
      for (int i = 32; i < 64; i++) { uint32_t c; asm volatile("mov.b32 %0, %1;" : "=r"(c) : "f"(S1[i])); S1[i] = __uint_as_float(c); }
      PROF(38);
    }
    const int tid = threadIdx.x;
    if (tid == 0) {
      unsigned old = atomicAdd(&g_flags.done.v, 1);
      if (old == ep1 * NMAIN - 1) {
        asm volatile("st.relaxed.gpu.global.u32 [%0], %1;" :: "l"(&g_flags.epoch.v), "r"(ep1) : "memory");
      }
    }
    __syncwarp();
    cluster_sync();
  }
}

typedef CUresult (*PFN_encode)(CUtensorMap*, CUtensorMapDataType, cuuint32_t, void*, const cuuint64_t*, const cuuint64_t*,
                               const cuuint32_t*, const cuuint32_t*, CUtensorMapInterleave, CUtensorMapSwizzle,
                               CUtensorMapL2promotion, CUtensorMapFloatOOBfill);

CUtensorMap make_map(PFN_encode enc, const void* ptr, uint64_t inner, uint64_t outer, uint32_t box_inner, uint32_t box_outer,
                     CUtensorMapSwizzle swz = CU_TENSOR_MAP_SWIZZLE_128B) {
  CUtensorMap m;
  cuuint64_t dims[2] = {inner, outer};
  cuuint64_t strides[1] = {inner * 2};
  cuuint32_t box[2] = {box_inner, box_outer};
  cuuint32_t es[2] = {1, 1};
  enc(&m, CU_TENSOR_MAP_DATA_TYPE_BFLOAT16, 2, const_cast<void*>(ptr), dims, strides, box, es, CU_TENSOR_MAP_INTERLEAVE_NONE,
      swz, CU_TENSOR_MAP_L2_PROMOTION_L2_256B, CU_TENSOR_MAP_FLOAT_OOB_FILL_NONE);
  return m;
}

}

extern "C" void kernel_launch(void* const* d_in, const int* in_sizes, int n_in, void* d_out, int out_size) {
  (void)in_sizes; (void)n_in; (void)out_size;
  static PFN_encode enc = nullptr;
  if (!enc) {
    void* fn = nullptr;
    cudaDriverEntryPointQueryResult qr;
    cudaGetDriverEntryPoint("cuTensorMapEncodeTiled", &fn, cudaEnableDefault, &qr);
    enc = (PFN_encode)fn;
    cudaFuncSetAttribute(mega_kernel, cudaFuncAttributeMaxDynamicSharedMemorySize, SMEM_BYTES);
  }
  Params prm;
  prm.x0 = (const __nv_bfloat16*)d_in[0];
  prm.wA_qkv = (const __nv_bfloat16*)d_in[1];
  prm.wA_o = (const __nv_bfloat16*)d_in[2];
  prm.wB_qkv = (const __nv_bfloat16*)d_in[4];
  prm.wB_phi = (const __nv_bfloat16*)d_in[5];
  prm.wB_o = (const __nv_bfloat16*)d_in[6];
  prm.out = (__nv_bfloat16*)d_out;
  void *obuf = nullptr, *wf = nullptr;
  cudaGetSymbolAddress(&obuf, g_obuf);
  cudaGetSymbolAddress(&wf, g_wfold);
  CUtensorMap tm_x0 = make_map(enc, d_in[0], D_MODEL, S_LEN, 64, 128);
  CUtensorMap tm_xo = make_map(enc, d_out, D_MODEL, S_LEN, 64, 16);
  CUtensorMap tm_os = make_map(enc, obuf, D_MODEL, 2 * S_LEN, 64, 16);
  CUtensorMap tm_o = make_map(enc, obuf, D_MODEL, 2 * S_LEN, 64, 128);
  CUtensorMap tm_wf = make_map(enc, wf, 2048, D_MODEL, 64, 32);
  CUtensorMap tm_wqA = make_map(enc, d_in[1], 3 * D_MODEL, D_MODEL, 64, 32);
  CUtensorMap tm_wqB = make_map(enc, prm.wB_qkv, 3 * D_MODEL, D_MODEL, 64, 32);
  CUtensorMap tm_woA = make_map(enc, prm.wA_o, D_MODEL, D_MODEL, 64, 64);
  CUtensorMap tm_woB = make_map(enc, prm.wB_o, D_MODEL, D_MODEL, 64, 64);
  CUtensorMap tm_phi = make_map(enc, prm.wB_phi, 32, 1024, 32, 128, CU_TENSOR_MAP_SWIZZLE_64B);
  mega_kernel<<<NMAIN + NAUX, 384, SMEM_BYTES>>>(tm_x0, tm_xo, tm_os, tm_o, tm_wf, tm_wqA, tm_wqB, tm_woA, tm_woB, tm_phi, prm);
}
```

```cpp
#include <cuda_runtime.h>
#include <cuda.h>
#include <cuda_bf16.h>
#include <stdint.h>

#define NLAYERS 4

#define STAG1 300
#define HPUMP1 2
#define HPUMP2 2
#define ASKEW 2
#define FPUMP 2
#define PFGAP 100
#define POLLW 4
#define POLL0 0
#define POLLGAP 120
#define KVLATE 0
#define BMASK 0x1F
#define ASITE 1
namespace {

constexpr int S_LEN = 2048, D_MODEL = 1024;
constexpr int NAUX = 4, NMAIN = 128;
constexpr int SLOT = 16384;
constexpr int QST = 24576;
constexpr int OFF_RA = 6 * SLOT, OFF_S = 10 * SLOT;
constexpr int OFF_HALO = 13 * SLOT, OFF_LNB = OFF_HALO  , OFF_ONES = OFF_HALO + 3072;
constexpr int OFF_ST = OFF_HALO + 7168  , OFF_PHI = OFF_HALO + 8192;
constexpr int OFF_BAR = 14 * SLOT;
constexpr int OFF_LNA = OFF_BAR + 1024;
constexpr int SMEM_BYTES = OFF_LNA + 2048;
#define WO_ASLOT(par) ((par) ? 0x98C6A7B398C6A98Cull : 0x98C76BA398C7698Cull)
constexpr unsigned long long WO_BSLOT = 0x5432105421054210ull;
__device__ __forceinline__ int kslice(int j, int i) { return i < 2 ? 2 * j + i : (i < 9 ? 2 * ((j + i - 1) & 7) : 2 * ((j + i) & 7) + 1); }
__device__ __forceinline__ int wslice(int j, int s) { return 2 * ((j + s) & 7) + (s >> 3); }
constexpr int KVH = 5 * 128 * 4;

struct __align__(128) Flag { unsigned v; unsigned pad[31]; };
struct Flags {
  Flag xready[4][16];
  Flag oready[4][16];
  Flag kvready[4][8][16];
  Flag wfready[8];
  Flag done;
  Flag epoch;
};

__device__ Flags g_flags;
__device__ __nv_bfloat16 g_obuf[2 * S_LEN * D_MODEL];
#define O_BIT(l) ((epoch * NLAYERS + (l) + 1) & 1u)
#define X_BIT(l) ((epoch * (NLAYERS - 1) + (l) + 1) & 1u)
__device__ __nv_bfloat16 g_wfold[D_MODEL * 2048];
__device__ uint4 g_halo[16 * 8 * 512];
__device__ float g_kv[2][32 * KVH];
__device__ __align__(128) uint2 g_colsum[2][1536][2];
__device__ __align__(128) uint2 g_stats[S_LEN * 8];
#define STAT_TAG(l) ((ep1 * NLAYERS + (l) + 1) & 3u)

#define RETRY_COUNT()
#define PROFL 1
#define PROFW 0
#define KVFLAG 1
#define PROFT(i) do {} while (0)
#define PROF(i) do {} while (0)

__device__ __forceinline__ uint32_t smem_u32(const void* p) { return (uint32_t)__cvta_generic_to_shared(p); }
__device__ __forceinline__ bool elect_one() {
  uint32_t p;
  asm volatile("{\n.reg .pred p;\nelect.sync _|p, 0xffffffff;\nselp.u32 %0, 1, 0, p;\n}\n" : "=r"(p));
  return p != 0;
}
__device__ __forceinline__ void mbar_init(uint32_t bar, uint32_t cnt) {
  asm volatile("mbarrier.init.shared::cta.b64 [%0], %1;" :: "r"(bar), "r"(cnt));
}
__device__ __forceinline__ void mbar_expect_tx(uint32_t bar, uint32_t bytes) {
  asm volatile("mbarrier.arrive.expect_tx.shared::cta.b64 _, [%0], %1;" :: "r"(bar), "r"(bytes) : "memory");
}
#define mbar_wait(bar, parity) \
  asm volatile("{\n.reg .pred p, q;\nW_%=:\nmbarrier.try_wait.parity.shared::cta.b64 p, [%1], %2;\nadd.s32 %0, %0, -1;\n" \
               "setp.gt.and.s32 q, %0, 0, !p;\n@q bra.uni W_%=;\n}\n" : "+r"(budget) : "r"((uint32_t)(bar)), "r"((uint32_t)(parity)) : "memory")
#define mbar_wait_sl(bar, parity) \
  asm volatile("{\n.reg .pred p, q;\nW_%=:\nmbarrier.try_wait.parity.shared::cta.b64 p, [%1], %2, 20000;\nadd.s32 %0, %0, -64;\n" \
               "setp.gt.and.s32 q, %0, 0, !p;\n@q bra.uni W_%=;\n}\n" : "+r"(budget) : "r"((uint32_t)(bar)), "r"((uint32_t)(parity)) : "memory")
__device__ __forceinline__ void mbar_arrive_local(uint32_t bar) {
  asm volatile("mbarrier.arrive.shared::cta.b64 _, [%0];" :: "r"(bar) : "memory");
}
__device__ __forceinline__ void tma_load_2d(uint32_t dst, const CUtensorMap* tm, uint32_t bar, int c0, int c1) {
  asm volatile("cp.async.bulk.tensor.2d.shared::cluster.global.mbarrier::complete_tx::bytes [%0], [%1, {%3, %4}], [%2];"
               :: "r"(dst), "l"(tm), "r"(bar), "r"(c0), "r"(c1) : "memory");
}
__device__ __forceinline__ void tma_load_2d_mc(uint32_t dst, const CUtensorMap* tm, uint32_t bar, int c0, int c1) {
  asm volatile("cp.async.bulk.tensor.2d.shared::cluster.global.mbarrier::complete_tx::bytes.multicast::cluster [%0], [%1, {%3, %4}], [%2], %5;"
               :: "r"(dst), "l"(tm), "r"(bar), "r"(c0), "r"(c1), "h"((uint16_t)3) : "memory");
}
__device__ __forceinline__ void tma_store_2d(const CUtensorMap* tm, uint32_t src, int c0, int c1) {
  asm volatile("cp.async.bulk.tensor.2d.global.shared::cta.bulk_group [%0, {%2, %3}], [%1];"
               :: "l"(tm), "r"(src), "r"(c0), "r"(c1) : "memory");
}
__device__ __forceinline__ void bulk_commit_wait() {
  asm volatile("cp.async.bulk.commit_group;\ncp.async.bulk.wait_group 0;" ::: "memory");
}
__device__ __forceinline__ void prefetch_tmap(const CUtensorMap* tm) {
  asm volatile("prefetch.tensormap [%0];" :: "l"(tm) : "memory");
}
__device__ __forceinline__ void fence_proxy_async_global() { asm volatile("fence.proxy.async.global;" ::: "memory"); }
__device__ __forceinline__ void fence_proxy_async_smem() { asm volatile("fence.proxy.async.shared::cta;" ::: "memory"); }
__device__ __forceinline__ unsigned ld_relaxed(const unsigned* p) {
  unsigned v;
  asm volatile("ld.relaxed.gpu.global.u32 %0, [%1];" : "=r"(v) : "l"(p) : "memory");
  return v;
}
__device__ __forceinline__ void fence_acquire() { asm volatile("fence.acquire.gpu;" ::: "memory"); }
__device__ __forceinline__ void wait_flag(const unsigned* p, unsigned target) {
  int it = 0;
  while ((int)(ld_relaxed(p) - target) < 0 && ++it < (1 << 20)) {}
  fence_acquire();
}
__device__ __forceinline__ void signal_release(unsigned* p) {
  asm volatile("red.release.gpu.global.add.u32 [%0], 1;" :: "l"(p) : "memory");
}
template <int ID, int N> __device__ __forceinline__ void bar_arrive() { asm volatile("bar.arrive %0, %1;" :: "n"(ID), "n"(N) : "memory"); }
template <int ID, int N> __device__ __forceinline__ void bar_sync() { asm volatile("bar.sync %0, %1;" :: "n"(ID), "n"(N) : "memory"); }
__device__ __forceinline__ void bar_wg(int wg) { asm volatile("bar.sync %0, 128;" :: "r"(2 + wg) : "memory"); }
__device__ __forceinline__ void cluster_sync() {
  asm volatile("barrier.cluster.arrive.relaxed.aligned;\nbarrier.cluster.wait.aligned;" ::: "memory");
}
__device__ __forceinline__ void cluster_wait() { asm volatile("barrier.cluster.wait.acquire.aligned;" ::: "memory"); }
enum { BAR_KV = 4  , BAR_O = 7  , BAR_WF = 12  , BAR_SKEW = 13 };

__device__ __forceinline__ void wgmma_fence() { asm volatile("wgmma.fence.sync.aligned;" ::: "memory"); }
__device__ __forceinline__ void wgmma_commit() { asm volatile("wgmma.commit_group.sync.aligned;" ::: "memory"); }
template <int N> __device__ __forceinline__ void wgmma_wait() { asm volatile("wgmma.wait_group.sync.aligned %0;" :: "n"(N) : "memory"); }

template <int scale_d, int tnsp_b = 1> __device__ __forceinline__ void wgmma_n192(float* d, uint64_t descA, uint64_t descB) {
  asm volatile("{\n.reg .pred p;\nsetp.ne.b32 p, %98, 0;\n"
               "wgmma.mma_async.sync.aligned.m64n192k16.f32.bf16.bf16 {%0,%1,%2,%3,%4,%5,%6,%7,%8,%9,%10,%11,%12,%13,%14,%15,%16,%17,%18,%19,%20,%21,%22,%23,%24,%25,%26,%27,%28,%29,%30,%31,%32,%33,%34,%35,%36,%37,%38,%39,%40,%41,%42,%43,%44,%45,%46,%47,%48,%49,%50,%51,%52,%53,%54,%55,%56,%57,%58,%59,%60,%61,%62,%63,%64,%65,%66,%67,%68,%69,%70,%71,%72,%73,%74,%75,%76,%77,%78,%79,%80,%81,%82,%83,%84,%85,%86,%87,%88,%89,%90,%91,%92,%93,%94,%95}, %96, %97, p, 1, 1, 0, %99;\n}\n"
               : "+f"(d[0]), "+f"(d[1]), "+f"(d[2]), "+f"(d[3]), "+f"(d[4]), "+f"(d[5]), "+f"(d[6]), "+f"(d[7]), "+f"(d[8]), "+f"(d[9]), "+f"(d[10]), "+f"(d[11]), "+f"(d[12]), "+f"(d[13]), "+f"(d[14]), "+f"(d[15]), "+f"(d[16]), "+f"(d[17]), "+f"(d[18]), "+f"(d[19]), "+f"(d[20]), "+f"(d[21]), "+f"(d[22]), "+f"(d[23]), "+f"(d[24]), "+f"(d[25]), "+f"(d[26]), "+f"(d[27]), "+f"(d[28]), "+f"(d[29]), "+f"(d[30]), "+f"(d[31]), "+f"(d[32]), "+f"(d[33]), "+f"(d[34]), "+f"(d[35]), "+f"(d[36]), "+f"(d[37]), "+f"(d[38]), "+f"(d[39]), "+f"(d[40]), "+f"(d[41]), "+f"(d[42]), "+f"(d[43]), "+f"(d[44]), "+f"(d[45]), "+f"(d[46]), "+f"(d[47]), "+f"(d[48]), "+f"(d[49]), "+f"(d[50]), "+f"(d[51]), "+f"(d[52]), "+f"(d[53]), "+f"(d[54]), "+f"(d[55]), "+f"(d[56]), "+f"(d[57]), "+f"(d[58]), "+f"(d[59]), "+f"(d[60]), "+f"(d[61]), "+f"(d[62]), "+f"(d[63]), "+f"(d[64]), "+f"(d[65]), "+f"(d[66]), "+f"(d[67]), "+f"(d[68]), "+f"(d[69]), "+f"(d[70]), "+f"(d[71]), "+f"(d[72]), "+f"(d[73]), "+f"(d[74]), "+f"(d[75]), "+f"(d[76]), "+f"(d[77]), "+f"(d[78]), "+f"(d[79]), "+f"(d[80]), "+f"(d[81]), "+f"(d[82]), "+f"(d[83]), "+f"(d[84]), "+f"(d[85]), "+f"(d[86]), "+f"(d[87]), "+f"(d[88]), "+f"(d[89]), "+f"(d[90]), "+f"(d[91]), "+f"(d[92]), "+f"(d[93]), "+f"(d[94]), "+f"(d[95])
               : "l"(descA), "l"(descB), "n"(scale_d), "n"(tnsp_b));
}
template <int scale_d> __device__ __forceinline__ void wgmma4_n192(float* d, uint32_t da, uint32_t db) {
#define R_ "{%0,%1,%2,%3,%4,%5,%6,%7,%8,%9,%10,%11,%12,%13,%14,%15,%16,%17,%18,%19,%20,%21,%22,%23,%24,%25,%26,%27,%28,%29,%30,%31,%32,%33,%34,%35,%36,%37,%38,%39,%40,%41,%42,%43,%44,%45,%46,%47,%48,%49,%50,%51,%52,%53,%54,%55,%56,%57,%58,%59,%60,%61,%62,%63,%64,%65,%66,%67,%68,%69,%70,%71,%72,%73,%74,%75,%76,%77,%78,%79,%80,%81,%82,%83,%84,%85,%86,%87,%88,%89,%90,%91,%92,%93,%94,%95}"
  asm volatile("{\n.reg .pred p, q;\n.reg .b64 a, b;\nsetp.ne.b32 p, %98, 0;\nsetp.eq.b32 q, 0, 0;\nmov.b64 a, {%96, 0x40000040};\nmov.b64 b, {%97, 0x40000040};\n"
               "wgmma.mma_async.sync.aligned.m64n192k16.f32.bf16.bf16 " R_ ", a, b, p, 1, 1, 0, 1;\nadd.s64 a, a, 2;\nadd.s64 b, b, 128;\n"
               "wgmma.mma_async.sync.aligned.m64n192k16.f32.bf16.bf16 " R_ ", a, b, q, 1, 1, 0, 1;\nadd.s64 a, a, 2;\nadd.s64 b, b, 128;\n"
               "wgmma.mma_async.sync.aligned.m64n192k16.f32.bf16.bf16 " R_ ", a, b, q, 1, 1, 0, 1;\nadd.s64 a, a, 2;\nadd.s64 b, b, 128;\n"
               "wgmma.mma_async.sync.aligned.m64n192k16.f32.bf16.bf16 " R_ ", a, b, q, 1, 1, 0, 1;\n}\n"
               : "+f"(d[0]), "+f"(d[1]), "+f"(d[2]), "+f"(d[3]), "+f"(d[4]), "+f"(d[5]), "+f"(d[6]), "+f"(d[7]), "+f"(d[8]), "+f"(d[9]), "+f"(d[10]), "+f"(d[11]), "+f"(d[12]), "+f"(d[13]), "+f"(d[14]), "+f"(d[15]), "+f"(d[16]), "+f"(d[17]), "+f"(d[18]), "+f"(d[19]), "+f"(d[20]), "+f"(d[21]), "+f"(d[22]), "+f"(d[23]), "+f"(d[24]), "+f"(d[25]), "+f"(d[26]), "+f"(d[27]), "+f"(d[28]), "+f"(d[29]), "+f"(d[30]), "+f"(d[31]), "+f"(d[32]), "+f"(d[33]), "+f"(d[34]), "+f"(d[35]), "+f"(d[36]), "+f"(d[37]), "+f"(d[38]), "+f"(d[39]), "+f"(d[40]), "+f"(d[41]), "+f"(d[42]), "+f"(d[43]), "+f"(d[44]), "+f"(d[45]), "+f"(d[46]), "+f"(d[47]), "+f"(d[48]), "+f"(d[49]), "+f"(d[50]), "+f"(d[51]), "+f"(d[52]), "+f"(d[53]), "+f"(d[54]), "+f"(d[55]), "+f"(d[56]), "+f"(d[57]), "+f"(d[58]), "+f"(d[59]), "+f"(d[60]), "+f"(d[61]), "+f"(d[62]), "+f"(d[63]), "+f"(d[64]), "+f"(d[65]), "+f"(d[66]), "+f"(d[67]), "+f"(d[68]), "+f"(d[69]), "+f"(d[70]), "+f"(d[71]), "+f"(d[72]), "+f"(d[73]), "+f"(d[74]), "+f"(d[75]), "+f"(d[76]), "+f"(d[77]), "+f"(d[78]), "+f"(d[79]), "+f"(d[80]), "+f"(d[81]), "+f"(d[82]), "+f"(d[83]), "+f"(d[84]), "+f"(d[85]), "+f"(d[86]), "+f"(d[87]), "+f"(d[88]), "+f"(d[89]), "+f"(d[90]), "+f"(d[91]), "+f"(d[92]), "+f"(d[93]), "+f"(d[94]), "+f"(d[95])
               : "r"(da), "r"(db), "n"(scale_d));
#undef R_
}
template <int scale_d> __device__ __forceinline__ void wgmma4_n128(float* d, uint32_t da, uint32_t db) {
#define R_ "{%0,%1,%2,%3,%4,%5,%6,%7,%8,%9,%10,%11,%12,%13,%14,%15,%16,%17,%18,%19,%20,%21,%22,%23,%24,%25,%26,%27,%28,%29,%30,%31,%32,%33,%34,%35,%36,%37,%38,%39,%40,%41,%42,%43,%44,%45,%46,%47,%48,%49,%50,%51,%52,%53,%54,%55,%56,%57,%58,%59,%60,%61,%62,%63}"
  asm volatile("{\n.reg .pred p, q;\n.reg .b64 a, b;\nsetp.ne.b32 p, %66, 0;\nsetp.eq.b32 q, 0, 0;\nmov.b64 a, {%64, 0x40000040};\nmov.b64 b, {%65, 0x40000040};\n"
               "wgmma.mma_async.sync.aligned.m64n128k16.f32.bf16.bf16 " R_ ", a, b, p, 1, 1, 0, 1;\nadd.s64 a, a, 2;\nadd.s64 b, b, 128;\n"
               "wgmma.mma_async.sync.aligned.m64n128k16.f32.bf16.bf16 " R_ ", a, b, q, 1, 1, 0, 1;\nadd.s64 a, a, 2;\nadd.s64 b, b, 128;\n"
               "wgmma.mma_async.sync.aligned.m64n128k16.f32.bf16.bf16 " R_ ", a, b, q, 1, 1, 0, 1;\nadd.s64 a, a, 2;\nadd.s64 b, b, 128;\n"
               "wgmma.mma_async.sync.aligned.m64n128k16.f32.bf16.bf16 " R_ ", a, b, q, 1, 1, 0, 1;\n}\n"
               : "+f"(d[0]), "+f"(d[1]), "+f"(d[2]), "+f"(d[3]), "+f"(d[4]), "+f"(d[5]), "+f"(d[6]), "+f"(d[7]), "+f"(d[8]), "+f"(d[9]), "+f"(d[10]), "+f"(d[11]), "+f"(d[12]), "+f"(d[13]), "+f"(d[14]), "+f"(d[15]), "+f"(d[16]), "+f"(d[17]), "+f"(d[18]), "+f"(d[19]), "+f"(d[20]), "+f"(d[21]), "+f"(d[22]), "+f"(d[23]), "+f"(d[24]), "+f"(d[25]), "+f"(d[26]), "+f"(d[27]), "+f"(d[28]), "+f"(d[29]), "+f"(d[30]), "+f"(d[31]), "+f"(d[32]), "+f"(d[33]), "+f"(d[34]), "+f"(d[35]), "+f"(d[36]), "+f"(d[37]), "+f"(d[38]), "+f"(d[39]), "+f"(d[40]), "+f"(d[41]), "+f"(d[42]), "+f"(d[43]), "+f"(d[44]), "+f"(d[45]), "+f"(d[46]), "+f"(d[47]), "+f"(d[48]), "+f"(d[49]), "+f"(d[50]), "+f"(d[51]), "+f"(d[52]), "+f"(d[53]), "+f"(d[54]), "+f"(d[55]), "+f"(d[56]), "+f"(d[57]), "+f"(d[58]), "+f"(d[59]), "+f"(d[60]), "+f"(d[61]), "+f"(d[62]), "+f"(d[63])
               : "r"(da), "r"(db), "n"(scale_d));
#undef R_
}
template <int scale_d> __device__ __forceinline__ void wgmma_n32(float* d, uint64_t descA, uint64_t descB) {
  asm volatile("{\n.reg .pred p;\nsetp.ne.b32 p, %18, 0;\n"
               "wgmma.mma_async.sync.aligned.m64n32k16.f32.bf16.bf16 {%0,%1,%2,%3,%4,%5,%6,%7,%8,%9,%10,%11,%12,%13,%14,%15}, %16, %17, p, 1, 1, 0, 1;\n}\n"
               : "+f"(d[0]), "+f"(d[1]), "+f"(d[2]), "+f"(d[3]), "+f"(d[4]), "+f"(d[5]), "+f"(d[6]), "+f"(d[7]), "+f"(d[8]), "+f"(d[9]), "+f"(d[10]), "+f"(d[11]), "+f"(d[12]), "+f"(d[13]), "+f"(d[14]), "+f"(d[15])
               : "l"(descA), "l"(descB), "n"(scale_d));
}
template <int scale_d, int tnsp_a> __device__ __forceinline__ void wgmma_n40(float* d, uint64_t descA, uint64_t descB) {
  asm volatile("{\n.reg .pred p;\nsetp.ne.b32 p, %22, 0;\n"
               "wgmma.mma_async.sync.aligned.m64n40k16.f32.bf16.bf16 {%0,%1,%2,%3,%4,%5,%6,%7,%8,%9,%10,%11,%12,%13,%14,%15,%16,%17,%18,%19}, %20, %21, p, 1, 1, %23, 1;\n}\n"
               : "+f"(d[0]), "+f"(d[1]), "+f"(d[2]), "+f"(d[3]), "+f"(d[4]), "+f"(d[5]), "+f"(d[6]), "+f"(d[7]), "+f"(d[8]), "+f"(d[9]), "+f"(d[10]), "+f"(d[11]), "+f"(d[12]), "+f"(d[13]), "+f"(d[14]), "+f"(d[15]), "+f"(d[16]), "+f"(d[17]), "+f"(d[18]), "+f"(d[19])
               : "l"(descA), "l"(descB), "n"(scale_d), "n"(tnsp_a));
}
template <int scale_d> __device__ __forceinline__ void wgmma_n40_rs(float* d, const uint32_t* a, uint64_t descB) {
  asm volatile("{\n.reg .pred p;\nsetp.ne.b32 p, %25, 0;\n"
               "wgmma.mma_async.sync.aligned.m64n40k16.f32.bf16.bf16 {%0,%1,%2,%3,%4,%5,%6,%7,%8,%9,%10,%11,%12,%13,%14,%15,%16,%17,%18,%19}, {%20,%21,%22,%23}, %24, p, 1, 1, 1;\n}\n"
               : "+f"(d[0]), "+f"(d[1]), "+f"(d[2]), "+f"(d[3]), "+f"(d[4]), "+f"(d[5]), "+f"(d[6]), "+f"(d[7]), "+f"(d[8]), "+f"(d[9]), "+f"(d[10]), "+f"(d[11]), "+f"(d[12]), "+f"(d[13]), "+f"(d[14]), "+f"(d[15]), "+f"(d[16]), "+f"(d[17]), "+f"(d[18]), "+f"(d[19])
               : "r"(a[0]), "r"(a[1]), "r"(a[2]), "r"(a[3]), "l"(descB), "n"(scale_d));
}
__device__ __forceinline__ uint64_t make_desc(uint32_t addr, uint32_t lbo_bytes, uint32_t sbo_bytes) {
  return (uint64_t)((addr & 0x3FFFF) >> 4) | ((uint64_t)(lbo_bytes >> 4) << 16) | ((uint64_t)(sbo_bytes >> 4) << 32) | (1ull << 62);
}

__device__ __forceinline__ void ldsm_x4(uint32_t addr, uint32_t& r0, uint32_t& r1, uint32_t& r2, uint32_t& r3) {
  asm volatile("ldmatrix.sync.aligned.m8n8.x4.shared.b16 {%0,%1,%2,%3}, [%4];" : "=r"(r0), "=r"(r1), "=r"(r2), "=r"(r3) : "r"(addr) : "memory");
}
__device__ __forceinline__ void ldsm_x4_t(uint32_t addr, uint32_t& r0, uint32_t& r1, uint32_t& r2, uint32_t& r3) {
  asm volatile("ldmatrix.sync.aligned.m8n8.x4.trans.shared.b16 {%0,%1,%2,%3}, [%4];" : "=r"(r0), "=r"(r1), "=r"(r2), "=r"(r3) : "r"(addr) : "memory");
}
__device__ __forceinline__ void stsm_x4(uint32_t addr, uint32_t r0, uint32_t r1, uint32_t r2, uint32_t r3) {
  asm volatile("stmatrix.sync.aligned.m8n8.x4.shared.b16 [%0], {%1,%2,%3,%4};" :: "r"(addr), "r"(r0), "r"(r1), "r"(r2), "r"(r3) : "memory");
}
__device__ __forceinline__ void sts128(uint32_t addr, uint32_t a, uint32_t b, uint32_t c, uint32_t d) {
  asm volatile("st.shared.v4.u32 [%0], {%1,%2,%3,%4};" :: "r"(addr), "r"(a), "r"(b), "r"(c), "r"(d) : "memory");
}
__device__ __forceinline__ float lds32f(uint32_t addr) {
  float v;
  asm volatile("ld.shared.f32 %0, [%1];" : "=f"(v) : "r"(addr) : "memory");
  return v;
}
__device__ __forceinline__ void sts32f(uint32_t addr, float a) {
  asm volatile("st.shared.f32 [%0], %1;" :: "r"(addr), "f"(a) : "memory");
}
__device__ __forceinline__ void mma_bf16(float (&c)[4], uint32_t a0, uint32_t a1, uint32_t a2, uint32_t a3, uint32_t b0, uint32_t b1) {
  asm volatile("mma.sync.aligned.m16n8k16.row.col.f32.bf16.bf16.f32 {%0,%1,%2,%3}, {%4,%5,%6,%7}, {%8,%9}, {%0,%1,%2,%3};"
               : "+f"(c[0]), "+f"(c[1]), "+f"(c[2]), "+f"(c[3]) : "r"(a0), "r"(a1), "r"(a2), "r"(a3), "r"(b0), "r"(b1));
}
__device__ __forceinline__ uint32_t pack_bf16(float lo, float hi) {
  uint32_t r;
  asm("cvt.rn.bf16x2.f32 %0, %1, %2;" : "=r"(r) : "f"(hi), "f"(lo));
  return r;
}
__device__ __forceinline__ float bf_lo(uint32_t v) { return __uint_as_float(v << 16); }
__device__ __forceinline__ float bf_hi(uint32_t v) { return __uint_as_float(v & 0xFFFF0000u); }
__device__ __forceinline__ void split3(float x, uint32_t& h, uint32_t& m, uint32_t& l) {
  h = pack_bf16(x, 0.f); x -= bf_lo(h);
  m = pack_bf16(x, 0.f); x -= bf_lo(m);
  l = pack_bf16(x, 0.f);
}
__device__ __forceinline__ float ex2(float x) { float r; asm("ex2.approx.ftz.f32 %0, %1;" : "=f"(r) : "f"(x)); return r; }
__device__ __forceinline__ float rcp_fast(float x) { float r; asm("rcp.approx.ftz.f32 %0, %1;" : "=f"(r) : "f"(x)); return r; }
__device__ __forceinline__ void red_v4(float* p, float a, float b, float c, float d) {
  asm volatile("red.global.add.v4.f32 [%0], {%1, %2, %3, %4};" :: "l"(p), "f"(a), "f"(b), "f"(c), "f"(d) : "memory");
}
__device__ __forceinline__ uint4 ld_ll(const uint4* p) {
  uint4 v;
  asm volatile("{\n.reg .b64 a, b;\nld.relaxed.gpu.global.v2.b64 {a, b}, [%4];\nmov.b64 {%0, %1}, a;\nmov.b64 {%2, %3}, b;\n}\n"
               : "=r"(v.x), "=r"(v.y), "=r"(v.z), "=r"(v.w) : "l"(p) : "memory");
  return v;
}
__device__ __forceinline__ void st_b64(uint2* p, uint32_t a, uint32_t b) {
  asm volatile("{\n.reg .b64 v;\nmov.b64 v, {%1, %2};\nst.relaxed.gpu.global.b64 [%0], v;\n}\n" :: "l"(p), "r"(a), "r"(b) : "memory");
}
__device__ __forceinline__ void st_b128(uint4* p, uint32_t a, uint32_t b, uint32_t c, uint32_t d) {
  asm volatile("{\n.reg .b128 v;\nmov.b128 v, {%1, %2, %3, %4};\nst.relaxed.gpu.global.b128 [%0], v;\n}\n" :: "l"(p), "r"(a), "r"(b), "r"(c), "r"(d) : "memory");
}
__device__ __forceinline__ uint4 ld_b128(const uint4* p) {
  uint4 v;
  asm volatile("{\n.reg .b128 v;\nld.relaxed.gpu.global.b128 v, [%4];\nmov.b128 {%0, %1, %2, %3}, v;\n}\n" : "=r"(v.x), "=r"(v.y), "=r"(v.z), "=r"(v.w) : "l"(p) : "memory");
  return v;
}

constexpr float LOG2E = 1.4426950408889634f;

struct Params {
  const __nv_bfloat16* x0;
  const __nv_bfloat16* wA_qkv;
  const __nv_bfloat16* wA_o;
  const __nv_bfloat16* wB_qkv;
  const __nv_bfloat16* wB_phi;
  const __nv_bfloat16* wB_o;
  __nv_bfloat16* out;
};

#define ACC_DEF(d, n) _Pragma("unroll") for (int i_ = 0; i_ < (n); i_++) asm volatile("" : "=f"(d[i_]))
#define ACC_FENCE(d, n) _Pragma("unroll") for (int i_ = 0; i_ < (n); i_++) asm volatile("" : "+f"(d[i_]) :: "memory")
#define PIN(a, n) _Pragma("unroll") for (int i_ = 0; i_ < (n); i_++) asm volatile("" : "+f"((a)[i_]))
#define PINU(a, n) _Pragma("unroll") for (int i_ = 0; i_ < (n); i_++) asm volatile("" : "+r"((a)[i_]))

#define STAGE64(acc, off, p0, KIND, SEND) { \
    uint32_t w_[4][4]; \
    _Pragma("unroll") for (int j_ = 0; j_ < 4; j_++) { \
      const int o_ = (off) + j_ * 8; \
      w_[j_][0] = pack_bf16(rs0 * acc[o_ + 0], rs0 * acc[o_ + 1]); \
      w_[j_][1] = pack_bf16(rs1 * acc[o_ + 2], rs1 * acc[o_ + 3]); \
      w_[j_][2] = pack_bf16(rs0 * acc[o_ + 4], rs0 * acc[o_ + 5]); \
      w_[j_][3] = pack_bf16(rs1 * acc[o_ + 6], rs1 * acc[o_ + 7]); \
    } \
    if ((SEND) && hsend) { \
      _Pragma("unroll") for (int j_ = 0; j_ < 4; j_++) { \
        w_[j_][0] = (w_[j_][0] & ~1u) | hbit; \
        st_b128(hbase + lane + ((KIND) * 4 + j_) * 32, w_[j_][0], w_[j_][1], w_[j_][2], w_[j_][3]); \
      } \
    } \
    _Pragma("unroll") for (int j_ = 0; j_ < 4; j_++) \
      stsm_x4((KIND) ? (p0) + (j_ >> 1) * 8192 + (srowoff >> 1) + ((((uint32_t)(j_ & 1) << 5) + lhi) ^ lsw2) \
                     : (p0) + srowoff + ((((uint32_t)j_ << 5) + lhi) ^ lsw), \
              w_[j_][0], w_[j_][1], w_[j_][2], w_[j_][3]); \
  }
#define RW(j) (((j) >> 1) * 4 + ((j) & 1))
__device__ __forceinline__ float rmax16(const float* p) {
  float m[4];
#pragma unroll
  for (int j = 0; j < 4; j++) m[j] = fmaxf(fmaxf(p[RW(j)], p[RW(j + 4)]), fmaxf(p[RW(j + 8)], p[RW(j + 12)]));
  const float r = fmaxf(fmaxf(m[0], m[1]), fmaxf(m[2], m[3]));
  return fmaxf(r, __shfl_xor_sync(0xffffffffu, r, 1));
}
__device__ __forceinline__ float rmin16(const float* p) {
  float m[4];
#pragma unroll
  for (int j = 0; j < 4; j++) m[j] = fminf(fminf(p[RW(j)], p[RW(j + 4)]), fminf(p[RW(j + 8)], p[RW(j + 12)]));
  const float r = fminf(fminf(m[0], m[1]), fminf(m[2], m[3]));
  return fminf(r, __shfl_xor_sync(0xffffffffu, r, 1));
}
__device__ __forceinline__ float exps16(float* o, const float* p, float c, float b) {
  float s[4];
#pragma unroll
  for (int j = 0; j < 16; j++) { o[j] = ex2(fmaf(p[RW(j)], c, b)); if (j < 4) s[j] = o[j]; else s[j & 3] += o[j]; }
  return (s[0] + s[1]) + (s[2] + s[3]);
}
__device__ __forceinline__ void store16(const float* e, float sum, uint32_t dst, uint32_t dsw, int c0) {
  const float inv = rcp_fast(sum + __shfl_xor_sync(0xffffffffu, sum, 1));
#pragma unroll
  for (int j = 0; j < 2; j++)
    sts128(dst + (((c0 + j) << 4) ^ dsw), pack_bf16(e[j * 8] * inv, e[j * 8 + 1] * inv), pack_bf16(e[j * 8 + 2] * inv, e[j * 8 + 3] * inv),
           pack_bf16(e[j * 8 + 4] * inv, e[j * 8 + 5] * inv), pack_bf16(e[j * 8 + 6] * inv, e[j * 8 + 7] * inv));
}
__device__ __forceinline__ void expp16(uint32_t* o, const float* p, float c0, float b0, float c1, float b1) {
#pragma unroll
  for (int j = 0; j < 8; j++) {
    const float c = (j & 1) ? c1 : c0, b = (j & 1) ? b1 : b0;
    o[j] = pack_bf16(ex2(fmaf(p[2 * j], c, b)), ex2(fmaf(p[2 * j + 1], c, b)));
  }
}
__device__ __forceinline__ void extrema(float* m, const float* p, float c0, float c1) {
#pragma unroll
  for (int i = 0; i < 4; i++) {
    const float* q = p + (i >> 1) * 16 + (i & 1) * 2;
    m[(i >> 1) * 4 + (i & 1)] = fminf(fminf(fminf(q[0], q[1]), fminf(q[4], q[5])), fminf(fminf(q[8], q[9]), fminf(q[12], q[13])));
    m[(i >> 1) * 4 + (i & 1) + 2] = fmaxf(fmaxf(fmaxf(q[0], q[1]), fmaxf(q[4], q[5])), fmaxf(fmaxf(q[8], q[9]), fmaxf(q[12], q[13])));
  }
#pragma unroll
  for (int o = 1; o <= 2; o <<= 1)
#pragma unroll
    for (int i = 0; i < 8; i++) { const float x = __shfl_xor_sync(0xffffffffu, m[i], o); m[i] = (i & 2) ? fmaxf(m[i], x) : fminf(m[i], x); }
#pragma unroll
  for (int i = 0; i < 8; i++) m[i] *= ((i & 2) ? -1.f : 1.f) * ((i & 1) ? c1 : c0);
}
#define SCHED_FENCE() asm volatile("pmevent 0;" ::: "memory")

__global__ void __cluster_dims__(2, 1, 1) __launch_bounds__(384, 1)
mega_kernel(const __grid_constant__ CUtensorMap tm_x0, const __grid_constant__ CUtensorMap tm_xo, const __grid_constant__ CUtensorMap tm_os,
            const __grid_constant__ CUtensorMap tm_o, const __grid_constant__ CUtensorMap tm_wf,
            const __grid_constant__ CUtensorMap tm_wqA, const __grid_constant__ CUtensorMap tm_wqB,
            const __grid_constant__ CUtensorMap tm_woA, const __grid_constant__ CUtensorMap tm_woB,
            const __grid_constant__ CUtensorMap tm_phi, const Params prm) {
  extern __shared__ __align__(1024) uint8_t smem_raw[];
  const uint32_t sbase = smem_u32(smem_raw);
  const uint32_t bar_full = sbase + OFF_BAR;
  const uint32_t bar_done = bar_full + 384;
  const uint32_t bar_stat = bar_full + 768, bar_stat2 = bar_full + 776, bar_epi = bar_full + 784, bar_phi = bar_full + 936  ;
  const uint32_t bar_xr = bar_full + 800, bar_lx = bar_full + 808, bar_kvf = bar_full + 816  , bar_stg = bar_full + 832;
  const uint32_t bar_chk = bar_full + 848;

  const int warp = __shfl_sync(0xffffffffu, threadIdx.x >> 5, 0), lane = threadIdx.x & 31;
  uint32_t rank;
  asm volatile("mov.u32 %0, %%cluster_ctarank;" : "=r"(rank));
  const int cta = (int)blockIdx.x - NAUX;
  const int cl = cta >> 1;
  const int jj = cl & 7, cc = cl >> 3;
  const int mm = cc * 2 + (int)rank;

#define LOAD_EPOCH() const unsigned epoch = ld_relaxed(&g_flags.epoch.v), ep1 = epoch + 1; (void)epoch
  int budget = 1 << 22;

  if (cta >= 0) {
    {
      const int tx = threadIdx.x;
      const __nv_bfloat16* pf = (tx < 128) ? prm.x0 + (size_t)(mm * 128 + tx) * D_MODEL + jj * 128
                                           : prm.wA_qkv + (size_t)(jj * 128 + (tx & 63)) * 3072 + ((tx - 128) >> 6) * 1024 + jj * 128 + rank * 64;
      if (tx < 320) asm volatile("prefetch.global.L2 [%0];" :: "l"(pf));
      else if (tx == 320) prefetch_tmap(&tm_x0);
      else if (tx == 352) prefetch_tmap(&tm_wqA);
      else if (tx == 383) asm volatile("prefetch.global.L2 [%0];" :: "l"(&g_flags.epoch.v));
    }
    if (elect_one()) {
#pragma unroll
      for (int i = 0; i < 4; i++) {
        const int u = warp * 4 + i;
        mbar_init(bar_full + u * 8, ((u >= 4 && u < 11) || u > 40) ? 2 : 1); mbar_init(bar_done + u * 8, 16);
      }
      mbar_init(bar_stat + warp * 16, 0x111111181182ull >> (4 * warp) & 15);
      mbar_init(bar_stat + warp * 16 + 8, 0x111111121811ull >> (4 * warp) & 15);
      asm volatile("fence.mbarrier_init.release.cluster;" ::: "memory");
    }
    __syncthreads();
    asm volatile("barrier.cluster.arrive.relaxed.aligned;" ::: "memory");
  }

  if (cta < 0) {
    LOAD_EPOCH();
    const uint32_t buf = sbase + warp * SLOT, bar = sbase + OFF_BAR + warp * 16;
    const uint32_t lsw = (lane & 7) << 4, lhi = (lane >> 4) << 4, lrow = (lane & 15) * 128;
    const bool el = elect_one();
    if (el) {
      mbar_init(bar, 1); mbar_init(bar + 8, 1);
      asm volatile("fence.mbarrier_init.release.cluster;" ::: "memory");
    }
#pragma unroll 1
    for (int rd = 0; rd < (NLAYERS > 1 ? 5 : 2); rd++) {
      if (rd >= 2 && warp >= 8) break;
      const int tk = rd < 2 ? blockIdx.x * 12 + warp : blockIdx.x * 8 + warp;
      const int half = tk & 1;
      const int blk = rd < 2 ? (tk >> 1) * 2 + rd : (4 - rd) * 16 + (tk >> 1);
      const CUtensorMap* tm = rd < 2 ? &tm_wqA : (rd == 2 ? &tm_wqB : &tm_wf);
      const int j0 = (blk & 15) >> 1;
#define AUX_LOAD(n) { const uint32_t d_ = buf + ((n) & 1) * 8192, b_ = bar + ((n) & 1) * 8; const int r_ = kslice(j0, 2 * (n) + half) * 64; \
        mbar_expect_tx(b_, 8192); tma_load_2d(d_, tm, b_, blk * 64, r_); tma_load_2d(d_ + 4096, tm, b_, blk * 64, r_ + 32); }
      if (el) {
        if (rd == 3) { wait_flag(&g_flags.wfready[j0].v, ep1 * 16); fence_proxy_async_global(); }
        AUX_LOAD(0); AUX_LOAD(1);
      }
      __syncwarp();
      float cs[8][4];
#pragma unroll
      for (int i = 0; i < 8; i++) cs[i][0] = cs[i][1] = cs[i][2] = cs[i][3] = 0.f;
#pragma unroll 1
      for (int n = 0; n < 8; n++) {
        const uint32_t tb = buf + (n & 1) * 8192 + lrow;
        mbar_wait(bar + (n & 1) * 8, (n >> 1) & 1);
#pragma unroll
        for (int i = 0; i < 16; i++) {
          uint32_t b0, b1, b2, b3;
          ldsm_x4_t(tb + (i >> 2) * 2048 + (((i & 3) * 32 + lhi) ^ lsw), b0, b1, b2, b3);
          mma_bf16(cs[2 * (i & 3)], 0x3F803F80u, 0x3F803F80u, 0x3F803F80u, 0x3F803F80u, b0, b1);
          mma_bf16(cs[2 * (i & 3) + 1], 0x3F803F80u, 0x3F803F80u, 0x3F803F80u, 0x3F803F80u, b2, b3);
        }
        __syncwarp();
        if (el && n < 6) AUX_LOAD(n + 2);
        __syncwarp();
      }
      if (lane < 4) {
#pragma unroll
        for (int i = 0; i < 8; i++) st_b64(&g_colsum[rd >= 2][blk * 32 + i * 4 + lane][half], __float_as_uint(cs[i][0]), (__float_as_uint(cs[i][1]) & ~3u) | (ep1 & 3));
      }
      __syncwarp();
    }
  } else if (warp >= 8) {
    asm volatile("setmaxnreg.dec.sync.aligned.u32 40;");
    if (warp == 8) {
      const bool el = elect_one();
      cluster_wait();
      if (el) {
#pragma unroll 1
        for (int l = 0; l < NLAYERS; l++) {
          const uint32_t par = l & 1;
          const CUtensorMap* tqk = par ? &tm_wf : &tm_wqA;
          const CUtensorMap* tv = par ? &tm_wqB : &tm_wqA;
          const CUtensorMap* two = par ? &tm_woB : &tm_woA;
          if (l == 1) { LOAD_EPOCH(); wait_flag(&g_flags.wfready[jj].v, ep1 * 16); fence_proxy_async_global(); }
#pragma unroll 1
          for (int u = 0; u < 32; u++) {
            if (u >= 4) mbar_wait_sl(bar_done + (u - 4) * 8, par);
            else if (l) mbar_wait_sl(bar_done + (43 + u + (u >> 1)) * 8, par ^ 1);
            else if (u == 1) __nanosleep(STAG1);
            else if (u == 2) mbar_wait_sl(bar_full, 0);
            const uint32_t fb = bar_full + u * 8;
            const bool res = u < 4 ? (l || u >= 2) : (u < 11 || (u >= 18 && u < 22));
            mbar_expect_tx(fb, res ? QST : QST + SLOT);
            const int row = kslice(jj, u < 4 ? u & 1 : (u < 18 ? u - 2 : (u < 22 ? u - 6 : u - 20))) * 64 + (int)rank * 32;
            const int ps = u < 4 ? u >> 1 : (u >= 18), col = jj * 128 + ps * 64;
            const int c0 = par ? jj * 128 + (ps ? 0 : 1024) : col;
            const uint32_t dst = sbase + (u & 3) * QST + rank * 4096;
            tma_load_2d_mc(dst, tqk, fb, c0, row);
            tma_load_2d_mc(dst + 8192, tqk, fb, c0 + (par ? 64 : 1024), row);
            tma_load_2d_mc(dst + 16384, tv, fb, col + 2048, row);
            if (l == 0 && u < 4) PROFT(473 + u);
          }
#pragma unroll 1
          for (int s = 0; s < 16; s++) {
            if (s < 5) { if (s != 2 && s != 4) mbar_wait_sl(bar_done + (28 + s) * 8, par); }
            else if (s != 14) mbar_wait_sl(bar_done + (27 + s - (s == 15)) * 8, par);
            const uint32_t fb = bar_full + (32 + s) * 8;
            mbar_expect_tx(fb, (s && s < 8) ? 2 * SLOT : SLOT);
            tma_load_2d_mc(sbase + rank * 8192 + (uint32_t)((WO_BSLOT >> (4 * s)) & 15) * SLOT, two, fb, jj * 128 + (int)rank * 64, wslice(jj, s) * 64);
            if (s >= 5 && s < 8) {
              if (s == 5) { mbar_wait_sl(bar_full + 33 * 8, par); fence_proxy_async_global(); }
              tma_load_2d(sbase + (uint32_t)((WO_ASLOT(par) >> (4 * s)) & 15) * SLOT, &tm_o, fb, wslice(jj, s) * 64, mm * 128);
            }
          }
        }
      }
      __syncwarp();
    } else if (warp == 9) {
      const bool el = elect_one();
      if (el) {
        PROFT(472);
        tma_load_2d(sbase + OFF_S, &tm_x0, bar_full, jj * 128, mm * 128);
        __nanosleep(STAG1);
        tma_load_2d(sbase + OFF_S + SLOT, &tm_x0, bar_full + 8, jj * 128 + 64, mm * 128);
      }
      __syncwarp();
      LOAD_EPOCH();
#pragma unroll 1
      for (int lp = 0; lp < 2 * NLAYERS; lp++) {
        const int l = lp >> 1, ph = lp & 1;
        const uint32_t par = l & 1;
        const __nv_bfloat16* pb = g_obuf + ph * 64 + (size_t)(mm * 128 + (ph ? 0 : S_LEN) + (lane & 7) * 16 + (jj & 1) * 8) * D_MODEL + (jj >> 1) * 16;
        const CUtensorMap* tm = lp ? &tm_o : &tm_x0;
        const int row = mm * 128 + ((ph || !l) ? 0 : S_LEN);
        const uint32_t bit = ph ? O_BIT(l) : X_BIT(l - 1);
        const uint32_t slots = ph ? (uint32_t)(WO_ASLOT(par) >> 36) : 0x8769876u;
        uint32_t rdy = lp ? 0 : 0xFF;
        mbar_wait_sl(ph ? bar_epi : (l ? bar_done + 47 * 8 : bar_full), ph ? par : (l ? par ^ 1 : 0));
#pragma unroll 1
        for (int i = 0; i < 7; i++) {
          if (!((rdy >> i) & 1)) {
            const unsigned* pp = reinterpret_cast<const unsigned*>(pb + ((jj + i + 1 + ((lane >> 3) & (POLLW - 1))) & 7) * 128);
            if (i == 0) __nanosleep(POLL0);
            unsigned v0 = ld_relaxed(pp);
            __nanosleep(POLLGAP);
            unsigned v1 = ld_relaxed(pp);
            uint32_t no;
#pragma unroll 1
            for (int it = 0; it < (1 << 18); it++) {
              no = __ballot_sync(0xffffffffu, (v0 ^ bit) & 1);
              if (!(no & 0xFF)) break;
              v0 = ld_relaxed(pp);
              no = __ballot_sync(0xffffffffu, (v1 ^ bit) & 1);
              if (!(no & 0xFF)) break;
              v1 = ld_relaxed(pp);
            }
            rdy = ((1 | (no & 0xFF00 ? 0 : 2) | (no & 0xFF0000 ? 0 : 4) | (no >> 24 ? 0 : 8)) & ((1 << POLLW) - 1)) << i;
          }
          if (i >= (ph ? 2 : 4)) mbar_wait_sl(bar_done + (i + (ph ? 33 : 0)) * 8, par);
          if (el) {
            if (i == 0) PROFT(320 + l * 16 + ph * 2);
            mbar_expect_tx(bar_chk + i * 8, SLOT);
            tma_load_2d(sbase + ((slots >> (4 * i)) & 15) * SLOT, tm, bar_chk + i * 8, ((jj + i + 1) & 7) * 128 + ph * 64, row);
          }
          __syncwarp();
        }
        if (ph == 0 && el) {
          if (l) { wait_flag(&g_flags.xready[l][mm].v, ep1 * 8); fence_proxy_async_global(); }
#pragma unroll 1
          for (int u = 11; u < 34; u++) {
            if (u == 18) u = 22;
            mbar_wait_sl(bar_done + (u - 4) * 8, par);
            if (u == 32) mbar_expect_tx(bar_xr, 2 * SLOT);
            tma_load_2d(sbase + OFF_RA + (u & 3) * SLOT, tm, u < 32 ? bar_full + u * 8 : bar_xr, kslice(jj, u < 18 ? u - 2 : (u < 32 ? u - 20 : u - 32)) * 64, row);
            if (l == 0 && u < 16 && NLAYERS > 1) {
              if (u == 11) { mbar_expect_tx(bar_phi, SLOT + 8192); tma_load_2d(sbase + OFF_PHI, &tm_phi, bar_phi, 0, jj * 128); }
              else tma_load_2d(sbase + 12 * SLOT + (u - 12) * 4096, &tm_wqB, bar_phi, jj * 128 + ((u - 12) >> 1) * 64, mm * 64 + (u & 1) * 32);
            }
          }
          wait_flag(&g_flags.oready[l][mm].v, ep1 * 8);
          fence_proxy_async_global();
          PROFT(321 + l * 16);
#pragma unroll 1
          for (int s = 1; s < 5; s++) {
            if (s < 3 || s == 3 + par) mbar_wait_sl(s < 3 ? bar_done + (29 + s) * 8 : bar_lx, par);
            tma_load_2d(sbase + (uint32_t)((WO_ASLOT(par) >> (4 * s)) & 15) * SLOT, &tm_o, bar_full + (32 + s) * 8, wslice(jj, s) * 64, mm * 128);
          }
        }
        __syncwarp();
      }
      cluster_wait();
    } else {
      const int hw = warp - 10;
      LOAD_EPOCH();
      const bool el = elect_one();
      cluster_wait();
      if (hw == 0) {
        mbar_wait_sl(bar_full + 8, 0);
        if (lane < 7) prefetch_tmap(lane == 0 ? &tm_os : lane == 1 ? &tm_o : lane == 2 ? &tm_wf : lane == 3 ? &tm_wqB : lane == 4 ? &tm_woA : lane == 5 ? &tm_woB : &tm_phi);
        if (lane < 4) asm volatile("prefetch.global.L2 [%0];" :: "l"(prm.wB_phi + jj * 4096 + mm * 256 + lane * 64));
#pragma unroll 1
        for (int i = 0; i < 8; i++) {
          asm volatile("prefetch.global.L2 [%0];" :: "l"(prm.wB_qkv + (size_t)(mm * 64 + (i & 3) * 16 + (lane >> 1)) * 3072 + (i >> 2) * 1024 + jj * 128 + (lane & 1) * 64));
          __nanosleep(PFGAP);
        }
      } else {
#pragma unroll 1
        for (int b = 0; b < 2; b++) {
          float4* z = reinterpret_cast<float4*>(g_kv[b] + (jj * 4) * KVH + mm * (4 * KVH / 16)) + lane;
#pragma unroll
          for (int i = 0; i < 5; i++) z[i * 32] = make_float4(0.f, 0.f, 0.f, 0.f);
        }
      }
      __syncwarp();
      uint32_t chkp = 0;
#pragma unroll 1
      for (int lp = 0; lp < 2 * NLAYERS; lp++) {
        const int l = lp >> 1, ph = lp & 1;
        const uint32_t par = l & 1;
        int lane; asm volatile("mov.u32 %0, %%laneid;" : "=r"(lane));
        if (hw) {
          const uint32_t bit = ph ? O_BIT(l) : X_BIT(l - 1);
          const uint32_t slots = ph ? (uint32_t)(WO_ASLOT(par) >> 36) : 0x8769876u;
#pragma unroll 1
          for (int c = 0; c < 7; c++) {
            const uint32_t tile = sbase + ((slots >> (4 * c)) & 15) * SLOT;
#pragma unroll 1
            for (int it = 0; it < (1 << 12); it++) {
              mbar_wait_sl(bar_chk + c * 8, (chkp >> c) & 1);
              chkp ^= 1u << c;
              if (el && c == 0) PROFT(488 + lp);
              if (lp == 0) break;
              uint32_t a1 = 1, o1 = 0;
#pragma unroll
              for (int i = 0; i < 16; i++) {
                uint32_t w;
                asm volatile("ld.shared.u32 %0, [%1];" : "=r"(w) : "r"(tile + i * 1024 + (lane & 7) * 132 + (lane >> 3) * 32) : "memory");
                a1 &= w; o1 |= w;
              }
              if (__all_sync(0xffffffffu, ((bit ? a1 : ~o1) & 1) != 0)) break;
              if (el) {
                fence_proxy_async_smem();
                mbar_expect_tx(bar_chk + c * 8, SLOT);
                tma_load_2d(tile, &tm_o, bar_chk + c * 8, ((jj + c + 1) & 7) * 128 + ph * 64, mm * 128 + (ph ? 0 : S_LEN));
                RETRY_COUNT();
              }
              __syncwarp();
            }
            if (el) mbar_arrive_local(bar_full + (c + (ph ? 41 : 4)) * 8);
            __syncwarp();
          }
          if (ph) continue;
#pragma unroll 1
          for (int hp = 0; hp < 2; hp++) {
            const uint4* src = reinterpret_cast<const uint4*>(g_colsum[par][jj * 64 + hp * 32 + lane]);
            uint32_t bad;
            int it = 0;
            float c[6];
            do {
              bad = 0;
#pragma unroll
              for (int p = 0; p < 3; p++) {
                const uint4 v = ld_ll(src + ((par && p < 2) ? (hp ? -32 : 512) + p * 32 : p * 512));
                bad |= (v.y ^ ep1) | (v.w ^ ep1);
                c[2 * p] = __uint_as_float(v.x) + __uint_as_float(v.z); c[2 * p + 1] = __uint_as_float(v.y) + __uint_as_float(v.w);
              }
              bad &= 3;
              if (bad) __nanosleep(300);
            } while (bad && ++it < (1 << 16));
#pragma unroll
            for (int p = 0; p < 6; p++) {
              uint32_t h, m, lo;
              split3(c[p], h, m, lo);
              sts128(sbase + OFF_LNB + hp * 4096 + (p >> 1) * 1024 + lane * 32 + (p & 1) * 16, h | (m << 16), h | (lo << 16), h | (m << 16), lo | (m << 16));
            }
            fence_proxy_async_smem();
            __syncwarp();
            if (el) { mbar_arrive_local(hp ? bar_stat2 : bar_stat); if (hp == 0) PROFT(324 + l * 16); }
            __syncwarp();
          }
        } else if (ph == 0) {
          mbar_wait_sl(bar_done + 24, par);
          const uint4* sp = reinterpret_cast<const uint4*>(g_stats + (size_t)(mm * 128) * 8) + lane;
#pragma unroll 1
          for (int hf = 0; hf < 4; hf++) {
            uint4 v[4];
            uint32_t bad;
            int it = 0;
            do {
              bad = 0;
#pragma unroll
              for (int i = 0; i < 4; i++) { v[i] = ld_ll(sp + (hf * 4 + i) * 32); bad |= (v[i].y ^ STAT_TAG(l)) | (v[i].w ^ STAT_TAG(l)); }
              bad &= 3;
              if (bad) __nanosleep(200);
            } while (bad && ++it < (1 << 16));
            __syncwarp();
            float mean = 0.f, m2 = 0.f;
#pragma unroll
            for (int i = 0; i < 4; i++) {
              float a = __uint_as_float(v[i].x) + __uint_as_float(v[i].z);
              a += __shfl_xor_sync(0xffffffffu, a, 1); a += __shfl_xor_sync(0xffffffffu, a, 2);
              a *= 0.125f;
              const float e0 = __uint_as_float(v[i].x) - a, e1 = __uint_as_float(v[i].z) - a;
              float q = fmaf(fmaf(e0, e0, e1 * e1), 128.f, __uint_as_float(v[i].y) + __uint_as_float(v[i].w));
              q += __shfl_xor_sync(0xffffffffu, q, 1); q += __shfl_xor_sync(0xffffffffu, q, 2);
              if ((lane & 3) == i) { mean = a; m2 = q; }
            }
            const uint32_t row = hf * 32 + (lane & 3) * 8 + (lane >> 2);
            uint32_t h, m, lo;
            split3(-0.5f * mean, h, m, lo);
            sts128(sbase + OFF_LNA + row * 16, h | (h << 16), m | (h << 16), lo | (m << 16), m | (lo << 16));
            sts32f(sbase + OFF_ST + row * 4, rsqrtf(m2 * (1.f / 1024.f) + 1e-5f));
          }
          fence_proxy_async_smem();
          __syncwarp();
          if (el) { mbar_arrive_local(bar_stat); PROFT(323 + l * 16); }
          __syncwarp();
#pragma unroll 1
          for (int i = 0; i < 8 - 4 * l; i++) {
            asm volatile("prefetch.global.L2 [%0];" :: "l"(i < 4 ? (l ? prm.wB_o : prm.wA_o) + (size_t)cta * 8192 + i * 2048 + lane * 64
                                                                 : prm.wB_qkv + (size_t)(cta * 8 + (i - 4) * 2 + (lane >> 4)) * 3072 + 2048 + (lane & 15) * 64));
            __nanosleep(PFGAP);
          }
          continue;
        }
        if (hw) {
          if (l & 1) {
#pragma unroll 1
            for (int h = 0; h < 2; h++) {
              asm volatile("bar.sync %0, 288;" :: "r"(BAR_KV + h) : "memory");
              __syncwarp();
              PROFT(331 + l * 16 + h);
              if (lane < 16) signal_release(&g_flags.kvready[(l & 2) + h][jj][lane].v);
              const unsigned* kf = &g_flags.kvready[(l & 2) + h][jj][mm].v;
              unsigned v0 = ld_relaxed(kf);
              __nanosleep(150);
              unsigned v1 = ld_relaxed(kf);
#pragma unroll 1
              for (int it = 0; it < (1 << 18); it++) {
                if (v0 == ep1 * 16) break;
                v0 = ld_relaxed(kf);
                if (v1 == ep1 * 16) break;
                v1 = ld_relaxed(kf);
              }
              fence_acquire();
              __syncwarp();
              if (el) { mbar_arrive_local(bar_kvf + h * 8); PROFT(333 + l * 16 + h); }
              __syncwarp();
            }
          }
        } else {
#pragma unroll 1
          for (uint32_t ev = l == NLAYERS - 1 ? 0x80u : (l == 0 ? 0x836054u : 0x830u); ev != 8; ev >>= 4) {
            const int e = ev & 15;
            asm volatile("bar.sync %0, 288;" :: "r"((0xFECA987 >> (4 * e)) & 15) : "memory");
            if (el) {
              if (e < 4) {
                PROFT(325 + l * 16 + e);
                tma_store_2d(&tm_o, sbase + (e ? 11 : 12) * SLOT, jj * 128 + (e & 1) * 64, mm * 128 + (e ? S_LEN : 0));
              } else {
                if (e == 5) mbar_expect_tx(bar_phi + 8, SLOT);
#pragma unroll 1
                for (int i = 0; i < 4; i++) {
                  const uint32_t a = sbase + (e > 4 ? 10 : 12) * SLOT + i * 4096;
                  const int c0 = (e > 4 ? 1024 : 0) + jj * 128 + (i >> 1) * 64, c1 = mm * 64 + (i & 1) * 32;
                  if (e == 5) tma_load_2d(a, &tm_wqB, bar_phi + 8, c0, c1); else tma_store_2d(&tm_wf, a, c0, c1);
                }
                if (e != 5) {
                  asm volatile("cp.async.bulk.commit_group;\ncp.async.bulk.wait_group.read 0;" ::: "memory");
                  mbar_arrive_local(bar_phi + (e - 4) * 4);
                }
              }
              if ((0x49 >> e) & 1) {
                bulk_commit_wait();
                signal_release(e == 0 ? &g_flags.oready[l][mm].v : e == 6 ? &g_flags.wfready[jj].v : &g_flags.xready[l + 1][mm].v);
              }
              if (e == 3) PROFT(330 + l * 16);
              if (e == 6) PROFT(335);
            }
            __syncwarp();
          }
        }
      }
    }
    cluster_sync();
  } else {
    asm volatile("setmaxnreg.inc.sync.aligned.u32 232;");
    LOAD_EPOCH();
    const int wg = warp >> 2;
    const int r0 = warp * 16;
    const uint32_t pK = sbase + OFF_S, pV = sbase + OFF_S + SLOT;
#define PMASKS(on, bit) const uint32_t pm0 = ((on) && t == (g & 3) && (g >> 2) == (g & 1)), pm1 = ((on) && t == (g & 3) && (g >> 2) != (g & 1)), pbit = (bit)
#define PBIT0(w) (((w) & ~pm0) | (pbit & pm0))
#define PBIT1(w) (((w) & ~pm1) | (pbit & pm1))
#define LANE_CONSTS() \
    int lane; asm volatile("mov.u32 %0, %%laneid;" : "=r"(lane)); \
    const int g = lane >> 2, t = lane & 3; \
    const uint32_t srowoff = (r0 + (lane & 15)) * 128, lsw = (lane & 7) << 4, lhi = (lane >> 4) << 4, lsw2 = (lane & 6) << 3; \
    (void)g; (void)t; (void)srowoff; (void)lsw; (void)lhi; (void)lsw2;
    uint32_t stgp = 0, peer;
    asm volatile("mapa.shared::cluster.u32 %0, %1, %2;" : "=r"(peer) : "r"(sbase), "r"(rank ^ 1));
    peer -= sbase;
    const uint32_t dA0 = (((sbase & 0x3FFFF) + wg * 8192) >> 4) | 0x10000u, dB0 = ((sbase & 0x3FFFF) >> 4) | 0x2000000u;
    cluster_wait();
#define STG_ARRIVE() { __syncwarp(); if (elect_one()) mbar_arrive_local(bar_stg); }
#define STG_WAIT() { mbar_wait(bar_stg, stgp); stgp ^= 1; }
#define PROFS() do {} while (0)
#define REL(addr) { if (elect_one()) { mbar_arrive_local(addr); asm volatile("mbarrier.arrive.shared::cluster.b64 _, [%0];" :: "r"((addr) + peer) : "memory"); } }
#define QSTEP(ACC, DA, SC, PRE) { \
      const uint32_t da = (DA), db = dB0 + (ub & 0x18) * (QST >> 7); \
      mbar_wait(ub, par); \
      PRE; \
      wgmma_fence(); \
      wgmma4_n192<SC>(ACC, da, db); \
      wgmma_commit(); PROFS(); }
#define QREL() { wgmma_wait<1>(); REL(ub + 376); ub += 8; }
#define RA_CUR (dA0 + (OFF_RA >> 4) + (ub & 0x18) * (SLOT >> 7))
#define PUMP1() { QSTEP(S1, RA_CUR, 1, {}); QREL(); }
#define PUMP0() { PUMP1(); SCHED_FENCE(); }
#define PUMP() if (h == 0) PUMP1()
#define WSTEP() { \
      const uint32_t s4 = (ub - bar_full - 256) >> 1; \
      const uint32_t da = dA0 + (((uint32_t)(WO_ASLOT(par) >> s4) & 15) << 10), db = dB0 + (((uint32_t)(WO_BSLOT >> s4) & 15) << 10); \
      mbar_wait(ub, par); \
      wgmma_fence(); \
      wgmma4_n128<1>(S1, da, db); \
      wgmma_commit(); PROFS(); \
      wgmma_wait<1>(); \
      if (s4) REL(ub + 376); \
      ub += 8; }
#define PUMPS(n) { _Pragma("unroll 1") for (int i_ = 0; i_ < (n); i_++) PUMP1(); }
#define SITE(n) { if ((BMASK >> (n)) & 1) PUMP1(); SCHED_FENCE(); }
#define LNSTEP(ACC, hh) { wgmma_fence(); wgmma_n192<1, 0>(ACC, make_desc(sbase + OFF_LNA + wg * 1024, 0, 128) ^ (1ull << 62), make_desc(sbase + OFF_LNB + (hh) * 4096, 0, 128) ^ (1ull << 62)); }
#define DRAIN_A(ACC, PMP) { \
      LANE_CONSTS(); \
      STAGE64(ACC, 64, pV, 1, 1); \
      PMP; \
      STAGE64(ACC, 32, pK, 0, 1); \
      STG_ARRIVE(); \
      _Pragma("unroll") for (int i_ = 0; i_ < 16; i_++) qa[i_] = pack_bf16(ACC[2 * i_], ACC[2 * i_ + 1]); \
      PINU(qa, 16); }
#define DRAIN_B(ACC) { \
      LANE_CONSTS(); \
      STAGE64(ACC, 64, pV, 1, 0); \
      _Pragma("unroll") for (int i_ = 0; i_ < 64; i_++) st[i_] = ACC[i_]; \
      PIN(st, 64); }
#define WARP_STORE(tm, tile, col, row) { fence_proxy_async_smem(); __syncwarp(); \
      if (elect_one()) { tma_store_2d(tm, (tile) + r0 * 128, col, (row) + r0); asm volatile("cp.async.bulk.commit_group;" ::: "memory"); } __syncwarp(); }
#define PUBLISH_O() { if (h) WARP_STORE(&tm_os, pO, jj * 128 + 64, mm * 128) else { fence_proxy_async_smem(); bar_arrive<BAR_O, 288>(); } }
#define X_OUT(pc, on) { \
      PMASKS(on, X_BIT(l)); \
      _Pragma("unroll") for (int j = (pc) * 4; j < (pc) * 4 + 4; j++) \
        stsm_x4(pK + (pc) * SLOT + srowoff + ((((uint32_t)(j & 3) << 5) + lhi) ^ lsw), \
                PBIT0(pack_bf16(S1[j * 8 + 0], S1[j * 8 + 1])), PBIT0(pack_bf16(S1[j * 8 + 2], S1[j * 8 + 3])), \
                PBIT1(pack_bf16(S1[j * 8 + 4], S1[j * 8 + 5])), PBIT1(pack_bf16(S1[j * 8 + 6], S1[j * 8 + 7]))); }
#define REST_P1(SKEW) { \
      mbar_wait(bar_stat2, par); \
      LNSTEP(S1, 1); \
      _Pragma("unroll 1") while (ub < bar_full + 256) { \
        if (ub == bar_full + 256 - 8 * (SKEW) && wg == 0) bar_sync<BAR_SKEW, 256>(); \
        QSTEP(S1, RA_CUR, 1, {}); \
        if (ub == bar_full + 248 && wg == 1) bar_arrive<BAR_SKEW, 256>(); \
        QREL(); \
      } \
      hbase += 256; \
      mbar_wait(bar_done + (31 - (SKEW)) * 8, par);        \
      wgmma_wait<0>(); \
      ACC_FENCE(S1, 96); \
      REL(bar_done + 31 * 8); \
      PROF(13); }
#define FOLD(tile, rd) { \
          LANE_CONSTS(); \
          float d[32]; \
          ACC_DEF(d, 32); \
          mbar_wait(bar_phi + (rd) * 8, 0); \
          wgmma_fence(); \
          _Pragma("unroll") for (int i = 0; i < 2; i++) { \
            const uint64_t da = make_desc((tile) + wg * 8192 + i * 64, 16, 1024); \
            const uint64_t db = make_desc(sbase + OFF_PHI + wg * 4096 + i * 2048, 16, 512) ^ (3ull << 62); \
            wgmma_n32<0>(d + i * 16, da, db); wgmma_n32<1>(d + i * 16, da + 2, db + 64); \
          } \
          wgmma_commit(); \
          PUMP0(); \
          ACC_FENCE(d, 32); \
          bar_wg(wg); \
          _Pragma("unroll") for (int i = 0; i < 4; i++) { \
            const float* x = d + (i & 1) * 8 + (i >> 1) * 2; \
            if (rd) sts128((tile) + wg * 8192 + ((warp & 3) * 16 + (i >> 1) * 8 + g) * 128 + (((2 * t + (i & 1)) ^ g) << 4), \
                           pack_bf16(x[0], x[1]), pack_bf16(x[4], x[5]), pack_bf16(x[16], x[17]), pack_bf16(x[20], x[21])); \
            else stsm_x4((tile) + srowoff + ((((uint32_t)i << 5) + lhi) ^ lsw), pack_bf16(d[i * 8], d[i * 8 + 1]), pack_bf16(d[i * 8 + 2], d[i * 8 + 3]), \
                         pack_bf16(d[i * 8 + 4], d[i * 8 + 5]), pack_bf16(d[i * 8 + 6], d[i * 8 + 7])); \
          } \
          fence_proxy_async_smem(); \
          bar_arrive<BAR_WF + 3 * (rd), 288>(); }
#define LOAD_X0(base) \
      _Pragma("unroll") for (int j = 0; j < 8; j++) { \
        uint32_t x0, x1, x2, x3; \
        ldsm_x4((base) + (j >> 2) * SLOT + srowoff + ((((uint32_t)(j & 3) << 5) + lhi) ^ lsw), x0, x1, x2, x3); \
        S1[j * 8 + 0] = bf_lo(x0); S1[j * 8 + 1] = bf_hi(x0); S1[j * 8 + 2] = bf_lo(x1); S1[j * 8 + 3] = bf_hi(x1); \
        S1[j * 8 + 4] = bf_lo(x2); S1[j * 8 + 5] = bf_hi(x2); S1[j * 8 + 6] = bf_lo(x3); S1[j * 8 + 7] = bf_hi(x3); \
      }
#define LOAD_X() { \
      wgmma_wait<0>(); \
      mbar_wait(bar_xr, par); \
      LOAD_X0(sbase + OFF_RA); \
      ACC_FENCE(S1, 64); \
      __syncwarp(); if (elect_one()) mbar_arrive_local(bar_lx); }

    float S1[96];
#pragma unroll
    for (int i = 0; i < 64; i++) S1[i] = 0.f;
#pragma unroll 1
    for (int l = 0; l < NLAYERS; l++) {
      const uint32_t par = l & 1;
      bar_wg(wg);
      PROF(0);
      uint32_t ub = bar_full;
      const bool hsend = (warp == 7) && (mm < 15);
      const uint32_t hbit = (NLAYERS > 2) ? (l == 0) : (ep1 & 1);
      float S0[96];
      {
        LANE_CONSTS();
        ACC_DEF(S0, 96);
        QSTEP(S0, dA0 + (OFF_S >> 4), 0, {});
        ub += 8;
        PROF(1);
        if (l == 0) { mbar_wait(ub, 0); LOAD_X0(pK); }
        else { X_OUT(1, false); fence_proxy_async_smem(); }
        SCHED_FENCE();
        {
          float a0 = S1[0], a1 = S1[2], b0 = S1[1], b1 = S1[3];
#pragma unroll
          for (int i = 4; i < 64; i += 4) { a0 += S1[i]; b0 += S1[i + 1]; a1 += S1[i + 2]; b1 += S1[i + 3]; }
          a0 += b0; a1 += b1;
          a0 += __shfl_xor_sync(0xffffffffu, a0, 1); a1 += __shfl_xor_sync(0xffffffffu, a1, 1);
          a0 += __shfl_xor_sync(0xffffffffu, a0, 2); a1 += __shfl_xor_sync(0xffffffffu, a1, 2);
          a0 *= (1.f / 128.f); a1 *= (1.f / 128.f);
          asm volatile("" : "+f"(a0), "+f"(a1));
          bar_wg(wg);
          QSTEP(S0, dA0 + ((OFF_S + SLOT) >> 4), 1, wgmma_wait<0>());
          REL(ub + 376); ub += 8;
          SCHED_FENCE();
          float q0 = 0.f, q1 = 0.f;
          b0 = 0.f; b1 = 0.f;
#pragma unroll
          for (int i = 0; i < 64; i += 4) {
            const float d0 = S1[i] - a0, d1 = S1[i + 1] - a0, d2 = S1[i + 2] - a1, d3 = S1[i + 3] - a1;
            q0 = fmaf(d0, d0, q0); b0 = fmaf(d1, d1, b0); q1 = fmaf(d2, d2, q1); b1 = fmaf(d3, d3, b1);
          }
          q0 += b0; q1 += b1;
          q0 += __shfl_xor_sync(0xffffffffu, q0, 1); q1 += __shfl_xor_sync(0xffffffffu, q1, 1);
          q0 += __shfl_xor_sync(0xffffffffu, q0, 2); q1 += __shfl_xor_sync(0xffffffffu, q1, 2);
          if (t < 2) st_b64(g_stats + (size_t)(mm * 128 + r0 + g + t * 8) * 8 + jj, __float_as_uint(t ? a1 : a0), (__float_as_uint(t ? q1 : q0) & ~3u) | STAT_TAG(l));
        }
        if (l) { asm volatile("cp.async.bulk.wait_group 0;" ::: "memory"); bar_arrive<BAR_O + 3, 288>(); }
        ACC_DEF(S1, 96);
        QSTEP(S1, dA0 + (OFF_S >> 4), 0, {});
        QREL();
        QSTEP(S1, dA0 + ((OFF_S + SLOT) >> 4), 1, {});
        QREL();
#pragma unroll 1
        for (int i = 0; i < 14; i++) {
          QSTEP(S0, RA_CUR, 1, {});
          if (i == 0) PROF(2);
          QREL();
        }
      }
      LANE_CONSTS();
      uint4* hbase = g_halo + (size_t)(mm * 8 + jj) * 512;
      mbar_wait(bar_stat, par);
      LNSTEP(S0, 0);
      wgmma_commit();
      const float rs0 = lds32f(sbase + OFF_ST + (r0 + g) * 4), rs1 = lds32f(sbase + OFF_ST + (r0 + g + 8) * 4);
      PUMP0();
      ACC_FENCE(S0, 96);
      PROF(3);
      if (!par) {
        constexpr uint32_t par = 0;
        uint32_t qa[16];
        DRAIN_A(S0, PUMP0());
#pragma unroll 1
        for (int h = 0; h < 2; h++) {
          const uint32_t pO = sbase + (h ? 3 : 12) * SLOT;
          PROF(4 + h * 12);
          const bool fold = (l == 0 && h == 0 && NLAYERS > 1);
          if (fold) FOLD(pO, 0) else if (h == 0) PUMPS(HPUMP1);
          LANE_CONSTS();
          uint4 hv[8];
#pragma unroll
          for (int i = 0; i < 8; i++) hv[i] = make_uint4(hbit, 0, 0, 0);
          const bool hrec = (warp == 0 && mm > 0);
          if (hrec) {
#pragma unroll
            for (int i = 0; i < 8; i++) hv[i] = ld_b128(hbase + lane - 8 * 512 + i * 32);
          }
          if (h) LOAD_X() else PUMPS(HPUMP2);
          const uint32_t halo = sbase + OFF_HALO;
          STG_WAIT();
          if (warp == 0) {
#pragma unroll 1
            for (int it = 0; it < (1 << 16); it++) {
              uint32_t bad = 0;
#pragma unroll
              for (int i = 0; i < 8; i++) bad |= hv[i].x ^ hbit;
              if (__all_sync(0xffffffffu, (bad & 1) == 0)) break;
#pragma unroll
              for (int i = 0; i < 8; i++) hv[i] = ld_b128(hbase + lane - 8 * 512 + i * 32);
            }
#pragma unroll
            for (int i = 0; i < 8; i++)
              stsm_x4(i < 4 ? halo + srowoff + ((((uint32_t)i << 5) + lhi) ^ lsw)
                            : halo + (srowoff >> 1) + (i >> 1) * 1024 + ((((uint32_t)(i & 1) << 5) + lhi) ^ lsw2), hv[i].x, hv[i].y, hv[i].z, hv[i].w);
            __syncwarp();
          }
          PROF(5 + h * 12);
          const uint32_t kb1 = pK + r0 * 128, vb1 = pV + r0 * 64;
          const uint32_t kb0 = r0 ? kb1 - 2048 : halo, vb0 = r0 ? vb1 - 1024 : halo + 2048;
          const uint32_t vhs = r0 ? 8192 : 1024;
          float s[2][4][4];
          {
            uint32_t kf[2][4][4];
#pragma unroll
            for (int i = 0; i < 8; i++) {
              const int hh = i >> 2, jb = i & 3;
              ldsm_x4(((jb < 2) ? kb0 : kb1) + ((jb & 1) * 8 + (lane & 7)) * 128 + ((hh * 64 + ((lane >> 3) << 4)) ^ lsw), kf[hh][jb][0], kf[hh][jb][1], kf[hh][jb][2], kf[hh][jb][3]);
              s[hh][jb][0] = s[hh][jb][1] = s[hh][jb][2] = s[hh][jb][3] = 0.f;
            }
#pragma unroll
            for (int ks = 0; ks < 2; ks++)
#pragma unroll
              for (int i = 0; i < 8; i++) {
                const int hh = i >> 2, jb = i & 3;
                mma_bf16(s[hh][jb], qa[hh * 8 + ks * 4], qa[hh * 8 + ks * 4 + 1], qa[hh * 8 + ks * 4 + 2], qa[hh * 8 + ks * 4 + 3], kf[hh][jb][ks * 2], kf[hh][jb][ks * 2 + 1]);
              }
          }
          PUMP();
          if (fold) bar_arrive<BAR_WF + 2, 288>();
          PROF(6 + h * 12);
          const bool e = g & 1, hb = (2 * t + (g & 1)) <= g;
          uint32_t vf[2][2][2][4];
#pragma unroll
          for (int i = 0; i < 8; i++) {
            const int hh = i >> 2, ks = (i >> 1) & 1, dp = i & 1;
            ldsm_x4_t((ks ? vb1 + hh * 8192 : vb0 + hh * vhs) + (lane & 15) * 64 + ((dp * 32 + lhi) ^ lsw2), vf[hh][ks][dp][0], vf[hh][ks][dp][1], vf[hh][ks][dp][2], vf[hh][ks][dp][3]);
          }
          float va[2][2], vb[2][2], mx[2][2];
#pragma unroll
          for (int hh = 0; hh < 2; hh++) {
            va[hh][0] = e ? s[hh][1][1] : s[hh][1][0];
            vb[hh][0] = hb ? (e ? s[hh][2][1] : s[hh][2][0]) : (e ? s[hh][0][1] : s[hh][0][0]);
            va[hh][1] = e ? s[hh][2][3] : s[hh][2][2];
            vb[hh][1] = hb ? (e ? s[hh][3][3] : s[hh][3][2]) : (e ? s[hh][1][3] : s[hh][1][2]);
          }
          if (warp == 0 && mm == 0) {
#pragma unroll
            for (int hh = 0; hh < 2; hh++) { va[hh][0] = -INFINITY; if (!hb) { vb[hh][0] = -INFINITY; vb[hh][1] = -INFINITY; } }
          }
#pragma unroll
          for (int i = 0; i < 4; i++) mx[i >> 1][i & 1] = fmaxf(va[i >> 1][i & 1], vb[i >> 1][i & 1]);
#pragma unroll
          for (int o = 1; o <= 2; o <<= 1)
#pragma unroll
            for (int i = 0; i < 4; i++) mx[i >> 1][i & 1] = fmaxf(mx[i >> 1][i & 1], __shfl_xor_sync(0xffffffffu, mx[i >> 1][i & 1], o));
          const float sc0 = rs0 * (0.17677669529663687f * LOG2E), sc1 = rs1 * (0.17677669529663687f * LOG2E);
#pragma unroll
          for (int i = 0; i < 4; i++) {
            const float sc = (i & 1) ? sc1 : sc0, m = mx[i >> 1][i & 1];
            va[i >> 1][i & 1] = ex2((va[i >> 1][i & 1] - m) * sc); vb[i >> 1][i & 1] = ex2((vb[i >> 1][i & 1] - m) * sc);
            mx[i >> 1][i & 1] = va[i >> 1][i & 1] + vb[i >> 1][i & 1];
          }
          if (h == 0 && ASITE) { PIN(&va[0][0], 4); PIN(&vb[0][0], 4); PIN(&mx[0][0], 4); PUMP1(); }
#pragma unroll
          for (int o = 1; o <= 2; o <<= 1)
#pragma unroll
            for (int i = 0; i < 4; i++) mx[i >> 1][i & 1] += __shfl_xor_sync(0xffffffffu, mx[i >> 1][i & 1], o);
          const uint32_t selA = e ? 0x1044 : 0x4410, selB = e ? 0x3244 : 0x4432, selL = hb ? 0x4444 : selB, selH = hb ? selB : 0x4444;
          float o[2][4][4];
          uint32_t pa[2][6];
#pragma unroll
          for (int hh = 0; hh < 2; hh++) {
            const float i0 = rcp_fast(mx[hh][0]), i1 = rcp_fast(mx[hh][1]);
            const uint32_t w0 = pack_bf16(va[hh][0] * i0, vb[hh][0] * i0), w1 = pack_bf16(va[hh][1] * i1, vb[hh][1] * i1);
            pa[hh][0] = __byte_perm(w0, 0, selL); pa[hh][1] = __byte_perm(w0, 0, selA); pa[hh][2] = __byte_perm(w1, 0, selL);
            pa[hh][3] = __byte_perm(w0, 0, selH); pa[hh][4] = __byte_perm(w1, 0, selA); pa[hh][5] = __byte_perm(w1, 0, selH);
#pragma unroll
            for (int dj = 0; dj < 4; dj++) { o[hh][dj][0] = o[hh][dj][1] = o[hh][dj][2] = o[hh][dj][3] = 0.f; }
          }
          PROF(7 + h * 12);
#pragma unroll
          for (int i = 0; i < 8; i++) mma_bf16(o[i >> 2][i & 3], pa[i >> 2][0], 0u, pa[i >> 2][1], pa[i >> 2][2], vf[i >> 2][0][(i >> 1) & 1][(i & 1) * 2], vf[i >> 2][0][(i >> 1) & 1][(i & 1) * 2 + 1]);
#pragma unroll
          for (int i = 0; i < 8; i++) mma_bf16(o[i >> 2][i & 3], pa[i >> 2][3], pa[i >> 2][4], 0u, pa[i >> 2][5], vf[i >> 2][1][(i >> 1) & 1][(i & 1) * 2], vf[i >> 2][1][(i >> 1) & 1][(i & 1) * 2 + 1]);
          if (h == 0) PUMP1() else mbar_wait(bar_done + 30 * 8, par);
          if (fold) mbar_wait(bar_phi, 1);
#pragma unroll
          for (int i = 0; i < 4; i++) {
            const int hh = i >> 1, dp = i & 1;
            PMASKS(h, O_BIT(l));
            stsm_x4(pO + srowoff + ((hh * 64 + dp * 32 + lhi) ^ lsw), PBIT0(pack_bf16(o[hh][dp * 2][0], o[hh][dp * 2][1])), PBIT0(pack_bf16(o[hh][dp * 2][2], o[hh][dp * 2][3])),
                    PBIT1(pack_bf16(o[hh][dp * 2 + 1][0], o[hh][dp * 2 + 1][1])), PBIT1(pack_bf16(o[hh][dp * 2 + 1][2], o[hh][dp * 2 + 1][3])));
          }
          PUBLISH_O();
          PROF(11 + h * 12);
          if (h) break;
          if (fold) { PUMPS(FPUMP); FOLD(pK, 1); }
          REST_P1(ASKEW);
          if (fold) mbar_wait(bar_phi + 8, 1);
          DRAIN_A(S1, {});
        }
      } else {
        constexpr uint32_t par = 1;
        float st[64];
        DRAIN_B(S0);
        if (warp < 2) sts128(sbase + OFF_ONES + warp * 512 + lane * 16, 0x3F803F80u, 0x3F803F80u, 0x3F803F80u, 0x3F803F80u);
        const float c0 = rs0 * LOG2E, c1 = rs1 * LOG2E;
#define KV_PART(hp, ...) { \
          float kv[20]; \
          ACC_DEF(kv, 20); \
          const uint64_t dp = make_desc(wg ? pK : sbase + 12 * SLOT, 16, 1024); \
          const uint64_t dv = (make_desc(pV + wg * 8192, OFF_ONES - OFF_S - SLOT - wg * 8192, 512) ^ (3ull << 62)); \
          constexpr uint64_t DVS = 64ull - (64ull << 16); \
          fence_proxy_async_smem(); \
          STG_ARRIVE(); \
          STG_WAIT(); \
          wgmma_fence(); \
          _Pragma("unroll") for (int ks = 0; ks < 8; ks++) { if (ks == 0) wgmma_n40<0, 1>(kv, dp, dv); else wgmma_n40<1, 1>(kv, dp + ks * 128, dv + ks * DVS); } \
          wgmma_commit(); \
          __VA_ARGS__; \
          ACC_FENCE(kv, 20); \
          float* kvg = g_kv[l >> 1] + (jj * 4 + (hp) * 2 + wg) * KVH + ((warp & 3) * 32 + lane) * 4; \
          _Pragma("unroll") for (int i = 0; i < 4; i++) red_v4(kvg + i * 512, kv[i * 4], kv[i * 4 + 1], kv[i * 4 + 2], kv[i * 4 + 3]); \
          if (t == 0) red_v4(kvg + 2048, kv[16], kv[17], kv[18], kv[19]); \
          bar_arrive<BAR_KV + (hp), 288>(); \
          STG_ARRIVE(); }
#pragma unroll 1
        for (int h = 0; h < 2; h++) {
          PROF(4 + h * 2);
          SITE(0);
          LANE_CONSTS();
          const uint32_t dsw = (uint32_t)(g ^ (2 * t)) << 4, dst = ((t & 2) ? pK : sbase + 12 * SLOT) + (r0 + g) * 128;
          float e[16], f[16];
          float mn0 = rmin16(st);
          asm volatile("" : "+f"(mn0)); SCHED_FENCE();
          float sa = exps16(e, st, -c0, mn0 * c0), mx0 = rmax16(st);
          asm volatile("" : "+f"(sa), "+f"(mx0)); PIN(e, 16); SITE(1);
          if (h) STG_WAIT();
          store16(e, sa, dst, dsw, 4);
          float sb = exps16(f, st, c0, -mx0 * c0), mn1 = rmin16(st + 2);
          asm volatile("" : "+f"(sb), "+f"(mn1)); PIN(f, 16); SITE(2);
          store16(f, sb, dst, dsw, 0);
          float sc = exps16(e, st + 2, -c1, mn1 * c1), mx1 = rmax16(st + 2);
          asm volatile("" : "+f"(sc), "+f"(mx1)); PIN(e, 16); SITE(3);
          store16(e, sc, dst + 1024, dsw, 4);
          float sd = exps16(f, st + 2, c1, -mx1 * c1);
          asm volatile("" : "+f"(sd)); PIN(f, 16); SITE(4);
          store16(f, sd, dst + 1024, dsw, 0);
          PROF(5 + h * 2);
          if (h) break;
          KV_PART(0, PUMP0());
#pragma unroll
          for (int i = 0; i < 32; i++) st[i] = st[32 + i];
        }
        REST_P1(1);
        float mq[16];
        {
          LANE_CONSTS();
          DRAIN_B(S1);
          PROF(16);
          KV_PART(1, { SCHED_FENCE(); extrema(mq, st, c0, c1); extrema(mq + 8, st + 32, c0, c1); PIN(mq, 16); wgmma_wait<0>(); });
          STG_WAIT();
          PROF(17);
        }
#pragma unroll 1
        for (int h = 0; h < 2; h++) {
          const uint32_t pO = sbase + (h ? 3 : 12) * SLOT, pT = h ? pV : pK;
          LANE_CONSTS();
          const float4* kvg = reinterpret_cast<const float4*>(g_kv[l >> 1] + (jj * 4 + h * 2 + wg) * KVH) + (warp & 3) * 32 + lane;
          float4 v[5];
          uint32_t fq[32];
          if (KVLATE) { expp16(fq, st, -c0, mq[0], -c1, mq[1]); expp16(fq + 8, st, c0, mq[2], c1, mq[3]); PINU(fq, 16); }
          mbar_wait(bar_kvf + h * 8, l >> 1);
          PROF(25 + h);
#pragma unroll
          for (int i = 0; i < 4; i++) v[i] = __ldcg(kvg + i * 128);
          v[4] = __ldcg(kvg + 512 - t);
          if (!KVLATE) { expp16(fq, st, -c0, mq[0], -c1, mq[1]); expp16(fq + 8, st, c0, mq[2], c1, mq[3]); PINU(fq, 16); }
          else { expp16(fq + 16, st + 16, -c0, mq[4], -c1, mq[5]); expp16(fq + 24, st + 16, c0, mq[6], c1, mq[7]); PINU(fq + 16, 16); }
          SCHED_FENCE();
          PROF(18 + h * 14);
          {
            const uint32_t e = lane & 7, jt = ((lane >> 1) & 4) + (e >> 1);
            const uint32_t row = ((((warp >> 1) ^ wg) & 1) << 5) + ((jt & 1) << 4) + ((warp & 1) << 3) + (jt & 6) + (e & 1);
            const uint32_t kd = pT + wg * 8192 + row * 128, ksw = (row & 7) << 4;
#pragma unroll
            for (int i = 0; i < 2; i++) {
              const float4 a = v[i * 2], b = v[i * 2 + 1];
              stsm_x4(kd + ((i * 32 + lhi) ^ ksw), pack_bf16(a.x, a.y), pack_bf16(a.z, a.w), pack_bf16(b.x, b.y), pack_bf16(b.z, b.w));
            }
            stsm_x4(kd + ((64u + lhi) ^ ksw), pack_bf16(v[4].x, 1.f), pack_bf16(v[4].z, 1.f), 0u, 0u);
          }
          fence_proxy_async_smem();
          STG_ARRIVE();
          if (!KVLATE) { expp16(fq + 16, st + 16, -c0, mq[4], -c1, mq[5]); PINU(fq + 16, 8); }
          float o[4][20];
          STG_WAIT();
          PROF(19 + h * 14);
#pragma unroll
          for (int hh = 0; hh < 2; hh++) {
            const uint64_t db = make_desc(pT + hh * 8192, 16, 1024);
            if (hh && !KVLATE) { SCHED_FENCE(); expp16(fq + 24, st + 16, c0, mq[6], c1, mq[7]); PINU(fq + 24, 8); }
            if (hh) { wgmma_wait<0>(); ACC_FENCE(o[0], 20); ACC_FENCE(o[1], 20); }
            ACC_DEF(o[hh * 2], 20); ACC_DEF(o[hh * 2 + 1], 20);
            wgmma_fence();
#pragma unroll
            for (int sg = 0; sg < 2; sg++) {
              wgmma_n40_rs<0>(o[hh * 2 + sg], fq + hh * 16 + sg * 8, db + (sg ^ 1) * 256);
              wgmma_n40_rs<1>(o[hh * 2 + sg], fq + hh * 16 + sg * 8 + 4, db + (sg ^ 1) * 256 + 128);
            }
            wgmma_commit();
          }
          PMASKS(h, O_BIT(l));
#pragma unroll
          for (int hh = 0; hh < 2; hh++) {
            if (hh) { wgmma_wait<0>(); ACC_FENCE(o[2], 20); ACC_FENCE(o[3], 20); } else SCHED_FENCE();
            const float* x = o[hh * 2];
            const float* y = o[hh * 2 + 1];
            const float rx0 = rcp_fast(x[17]), ry0 = rcp_fast(y[17]), rx1 = rcp_fast(x[19]), ry1 = rcp_fast(y[19]);
            const float i0 = rcp_fast(fmaf(x[16], rx0, y[16] * ry0) + 1e-6f), i1 = rcp_fast(fmaf(x[18], rx1, y[18] * ry1) + 1e-6f);
            const float ax0 = rx0 * i0, ay0 = ry0 * i0, ax1 = rx1 * i1, ay1 = ry1 * i1;
#pragma unroll
            for (int dp = 0; dp < 2; dp++)
              stsm_x4(pO + srowoff + ((hh * 64 + dp * 32 + lhi) ^ lsw),
                      PBIT0(pack_bf16(fmaf(x[dp * 8], ax0, y[dp * 8] * ay0), fmaf(x[dp * 8 + 1], ax0, y[dp * 8 + 1] * ay0))),
                      PBIT0(pack_bf16(fmaf(x[dp * 8 + 2], ax1, y[dp * 8 + 2] * ay1), fmaf(x[dp * 8 + 3], ax1, y[dp * 8 + 3] * ay1))),
                      PBIT1(pack_bf16(fmaf(x[dp * 8 + 4], ax0, y[dp * 8 + 4] * ay0), fmaf(x[dp * 8 + 5], ax0, y[dp * 8 + 5] * ay0))),
                      PBIT1(pack_bf16(fmaf(x[dp * 8 + 6], ax1, y[dp * 8 + 6] * ay1), fmaf(x[dp * 8 + 7], ax1, y[dp * 8 + 7] * ay1))));
          }
          PUBLISH_O();
          PROF(20 + h * 14);
          if (h) break;
#pragma unroll
          for (int i = 0; i < 32; i++) st[i] = st[32 + i];
#pragma unroll
          for (int i = 0; i < 8; i++) mq[i] = mq[8 + i];
        }
        LANE_CONSTS();
        LOAD_X();
      }
      __syncwarp();
      if (elect_one()) mbar_arrive_local(bar_epi);
      bar_wg(wg);
#pragma unroll 1
      while (ub < bar_full + 384) {
        WSTEP();
        if (ub == bar_full + 8 * 41) { asm volatile("cp.async.bulk.wait_group.read 0;" ::: "memory"); PROF(35); }
        if (ub == bar_full + 8 * 42) PROF(36);
      }
      wgmma_wait<0>();
      ACC_FENCE(S1, 64);
      REL(bar_done + 47 * 8);
      PROF(37);
      {
        LANE_CONSTS();
        X_OUT(0, l < NLAYERS - 1);
        WARP_STORE(l < NLAYERS - 1 ? &tm_os : &tm_xo, pK, jj * 128, mm * 128 + (l < NLAYERS - 1 ? S_LEN : 0));
        if (l == NLAYERS - 1) {
          X_OUT(1, false);
          WARP_STORE(&tm_xo, pV, jj * 128 + 64, mm * 128);
          asm volatile("cp.async.bulk.wait_group 0;" ::: "memory");
        }
      }
#pragma unroll
      for (int i = 32; i < 64; i++) { uint32_t c; asm volatile("mov.b32 %0, %1;" : "=r"(c) : "f"(S1[i])); S1[i] = __uint_as_float(c); }
      PROF(38);
    }
    const int tid = threadIdx.x;
    if (tid == 0) {
      unsigned old = atomicAdd(&g_flags.done.v, 1);
      if (old == ep1 * NMAIN - 1) {
        asm volatile("st.relaxed.gpu.global.u32 [%0], %1;" :: "l"(&g_flags.epoch.v), "r"(ep1) : "memory");
      }
    }
    __syncwarp();
    cluster_sync();
  }
}

typedef CUresult (*PFN_encode)(CUtensorMap*, CUtensorMapDataType, cuuint32_t, void*, const cuuint64_t*, const cuuint64_t*,
                               const cuuint32_t*, const cuuint32_t*, CUtensorMapInterleave, CUtensorMapSwizzle,
                               CUtensorMapL2promotion, CUtensorMapFloatOOBfill);

CUtensorMap make_map(PFN_encode enc, const void* ptr, uint64_t inner, uint64_t outer, uint32_t box_inner, uint32_t box_outer,
                     CUtensorMapSwizzle swz = CU_TENSOR_MAP_SWIZZLE_128B) {
  CUtensorMap m;
  cuuint64_t dims[2] = {inner, outer};
  cuuint64_t strides[1] = {inner * 2};
  cuuint32_t box[2] = {box_inner, box_outer};
  cuuint32_t es[2] = {1, 1};
  enc(&m, CU_TENSOR_MAP_DATA_TYPE_BFLOAT16, 2, const_cast<void*>(ptr), dims, strides, box, es, CU_TENSOR_MAP_INTERLEAVE_NONE,
      swz, CU_TENSOR_MAP_L2_PROMOTION_L2_256B, CU_TENSOR_MAP_FLOAT_OOB_FILL_NONE);
  return m;
}

}

extern "C" void kernel_launch(void* const* d_in, const int* in_sizes, int n_in, void* d_out, int out_size) {
  (void)in_sizes; (void)n_in; (void)out_size;
  static PFN_encode enc = nullptr;
  if (!enc) {
    void* fn = nullptr;
    cudaDriverEntryPointQueryResult qr;
    cudaGetDriverEntryPoint("cuTensorMapEncodeTiled", &fn, cudaEnableDefault, &qr);
    enc = (PFN_encode)fn;
    cudaFuncSetAttribute(mega_kernel, cudaFuncAttributeMaxDynamicSharedMemorySize, SMEM_BYTES);
  }
  Params prm;
  prm.x0 = (const __nv_bfloat16*)d_in[0];
  prm.wA_qkv = (const __nv_bfloat16*)d_in[1];
  prm.wA_o = (const __nv_bfloat16*)d_in[2];
  prm.wB_qkv = (const __nv_bfloat16*)d_in[4];
  prm.wB_phi = (const __nv_bfloat16*)d_in[5];
  prm.wB_o = (const __nv_bfloat16*)d_in[6];
  prm.out = (__nv_bfloat16*)d_out;
  void *obuf = nullptr, *wf = nullptr;
  cudaGetSymbolAddress(&obuf, g_obuf);
  cudaGetSymbolAddress(&wf, g_wfold);
  CUtensorMap tm_x0 = make_map(enc, d_in[0], D_MODEL, S_LEN, 64, 128);
  CUtensorMap tm_xo = make_map(enc, d_out, D_MODEL, S_LEN, 64, 16);
  CUtensorMap tm_os = make_map(enc, obuf, D_MODEL, 2 * S_LEN, 64, 16);
  CUtensorMap tm_o = make_map(enc, obuf, D_MODEL, 2 * S_LEN, 64, 128);
  CUtensorMap tm_wf = make_map(enc, wf, 2048, D_MODEL, 64, 32);
  CUtensorMap tm_wqA = make_map(enc, d_in[1], 3 * D_MODEL, D_MODEL, 64, 32);
  CUtensorMap tm_wqB = make_map(enc, prm.wB_qkv, 3 * D_MODEL, D_MODEL, 64, 32);
  CUtensorMap tm_woA = make_map(enc, prm.wA_o, D_MODEL, D_MODEL, 64, 64);
  CUtensorMap tm_woB = make_map(enc, prm.wB_o, D_MODEL, D_MODEL, 64, 64);
  CUtensorMap tm_phi = make_map(enc, prm.wB_phi, 32, 1024, 32, 128, CU_TENSOR_MAP_SWIZZLE_64B);
  mega_kernel<<<NMAIN + NAUX, 384, SMEM_BYTES>>>(tm_x0, tm_xo, tm_os, tm_o, tm_wf, tm_wqA, tm_wqB, tm_woA, tm_woB, tm_phi, prm);
}
```

```cpp
#include <cuda_runtime.h>
#include <cuda.h>
#include <cuda_bf16.h>
#include <stdint.h>

#define NLAYERS 4

#define STAG1 300
#define HPUMP1 2
#define HPUMP2 2
#define ASKEW 2
#define FPUMP 2
#define PFGAP 100
#define POLLW 4
#define POLL0 0
#define POLLGAP 120
#define KVLATE 0
#define BMASK 0x1F
#define ASITE 1
namespace {

constexpr int S_LEN = 2048, D_MODEL = 1024;
constexpr int NAUX = 4, NMAIN = 128;
constexpr int SLOT = 16384;
constexpr int QST = 24576;
constexpr int OFF_RA = 6 * SLOT, OFF_S = 10 * SLOT;
constexpr int OFF_HALO = 13 * SLOT, OFF_LNB = OFF_HALO  , OFF_ONES = OFF_HALO + 3072;
constexpr int OFF_ST = OFF_HALO + 7168  , OFF_PHI = OFF_HALO + 8192;
constexpr int OFF_BAR = 14 * SLOT;
constexpr int OFF_LNA = OFF_BAR + 1024;
constexpr int SMEM_BYTES = OFF_LNA + 2048;
#define WO_ASLOT(par) ((par) ? 0x98C6A7B398C6A98Cull : 0x98C76BA398C7698Cull)
constexpr unsigned long long WO_BSLOT = 0x5432105421054210ull;
__device__ __forceinline__ int kslice(int j, int i) { return i < 2 ? 2 * j + i : (i < 9 ? 2 * ((j + i - 1) & 7) : 2 * ((j + i) & 7) + 1); }
__device__ __forceinline__ int wslice(int j, int s) { return 2 * ((j + s) & 7) + (s >> 3); }
constexpr int KVH = 5 * 128 * 4;

struct __align__(128) Flag { unsigned v; unsigned pad[31]; };
struct Flags {
  Flag xready[4][16];
  Flag oready[4][16];
  Flag kvready[4][8][16];
  Flag wfready[8];
  Flag done;
  Flag epoch;
};

__device__ Flags g_flags;
__device__ __nv_bfloat16 g_obuf[2 * S_LEN * D_MODEL];
#define O_BIT(l) ((epoch * NLAYERS + (l) + 1) & 1u)
#define X_BIT(l) ((epoch * (NLAYERS - 1) + (l) + 1) & 1u)
__device__ __nv_bfloat16 g_wfold[D_MODEL * 2048];
__device__ uint4 g_halo[16 * 8 * 512];
__device__ float g_kv[2][32 * KVH];
__device__ __align__(128) uint2 g_colsum[2][1536][2];
__device__ __align__(128) uint2 g_stats[S_LEN * 8];
#define STAT_TAG(l) ((ep1 * NLAYERS + (l) + 1) & 3u)

#define RETRY_COUNT()
#define PROFL 1
#define PROFW 0
#define KVFLAG 1
#define PROFT(i) do {} while (0)
#define PROF(i) do {} while (0)

__device__ __forceinline__ uint32_t smem_u32(const void* p) { return (uint32_t)__cvta_generic_to_shared(p); }
__device__ __forceinline__ bool elect_one() {
  uint32_t p;
  asm volatile("{\n.reg .pred p;\nelect.sync _|p, 0xffffffff;\nselp.u32 %0, 1, 0, p;\n}\n" : "=r"(p));
  return p != 0;
}
__device__ __forceinline__ void mbar_init(uint32_t bar, uint32_t cnt) {
  asm volatile("mbarrier.init.shared::cta.b64 [%0], %1;" :: "r"(bar), "r"(cnt));
}
__device__ __forceinline__ void mbar_expect_tx(uint32_t bar, uint32_t bytes) {
  asm volatile("mbarrier.arrive.expect_tx.shared::cta.b64 _, [%0], %1;" :: "r"(bar), "r"(bytes) : "memory");
}
#define mbar_wait(bar, parity) \
  asm volatile("{\n.reg .pred p, q;\nW_%=:\nmbarrier.try_wait.parity.shared::cta.b64 p, [%1], %2;\nadd.s32 %0, %0, -1;\n" \
               "setp.gt.and.s32 q, %0, 0, !p;\n@q bra.uni W_%=;\n}\n" : "+r"(budget) : "r"((uint32_t)(bar)), "r"((uint32_t)(parity)) : "memory")
#define mbar_wait_sl(bar, parity) \
  asm volatile("{\n.reg .pred p, q;\nW_%=:\nmbarrier.try_wait.parity.shared::cta.b64 p, [%1], %2, 20000;\nadd.s32 %0, %0, -64;\n" \
               "setp.gt.and.s32 q, %0, 0, !p;\n@q bra.uni W_%=;\n}\n" : "+r"(budget) : "r"((uint32_t)(bar)), "r"((uint32_t)(parity)) : "memory")
__device__ __forceinline__ void mbar_arrive_local(uint32_t bar) {
  asm volatile("mbarrier.arrive.shared::cta.b64 _, [%0];" :: "r"(bar) : "memory");
}
__device__ __forceinline__ void tma_load_2d(uint32_t dst, const CUtensorMap* tm, uint32_t bar, int c0, int c1) {
  asm volatile("cp.async.bulk.tensor.2d.shared::cluster.global.mbarrier::complete_tx::bytes [%0], [%1, {%3, %4}], [%2];"
               :: "r"(dst), "l"(tm), "r"(bar), "r"(c0), "r"(c1) : "memory");
}
__device__ __forceinline__ void tma_load_2d_mc(uint32_t dst, const CUtensorMap* tm, uint32_t bar, int c0, int c1) {
  asm volatile("cp.async.bulk.tensor.2d.shared::cluster.global.mbarrier::complete_tx::bytes.multicast::cluster [%0], [%1, {%3, %4}], [%2], %5;"
               :: "r"(dst), "l"(tm), "r"(bar), "r"(c0), "r"(c1), "h"((uint16_t)3) : "memory");
}
__device__ __forceinline__ void tma_store_2d(const CUtensorMap* tm, uint32_t src, int c0, int c1) {
  asm volatile("cp.async.bulk.tensor.2d.global.shared::cta.bulk_group [%0, {%2, %3}], [%1];"
               :: "l"(tm), "r"(src), "r"(c0), "r"(c1) : "memory");
}
__device__ __forceinline__ void bulk_commit_wait() {
  asm volatile("cp.async.bulk.commit_group;\ncp.async.bulk.wait_group 0;" ::: "memory");
}
__device__ __forceinline__ void prefetch_tmap(const CUtensorMap* tm) {
  asm volatile("prefetch.tensormap [%0];" :: "l"(tm) : "memory");
}
__device__ __forceinline__ void fence_proxy_async_global() { asm volatile("fence.proxy.async.global;" ::: "memory"); }
__device__ __forceinline__ void fence_proxy_async_smem() { asm volatile("fence.proxy.async.shared::cta;" ::: "memory"); }
__device__ __forceinline__ unsigned ld_relaxed(const unsigned* p) {
  unsigned v;
  asm volatile("ld.relaxed.gpu.global.u32 %0, [%1];" : "=r"(v) : "l"(p) : "memory");
  return v;
}
__device__ __forceinline__ void fence_acquire() { asm volatile("fence.acquire.gpu;" ::: "memory"); }
__device__ __forceinline__ void wait_flag(const unsigned* p, unsigned target) {
  int it = 0;
  while ((int)(ld_relaxed(p) - target) < 0 && ++it < (1 << 20)) {}
  fence_acquire();
}
__device__ __forceinline__ void signal_release(unsigned* p) {
  asm volatile("red.release.gpu.global.add.u32 [%0], 1;" :: "l"(p) : "memory");
}
template <int ID, int N> __device__ __forceinline__ void bar_arrive() { asm volatile("bar.arrive %0, %1;" :: "n"(ID), "n"(N) : "memory"); }
template <int ID, int N> __device__ __forceinline__ void bar_sync() { asm volatile("bar.sync %0, %1;" :: "n"(ID), "n"(N) : "memory"); }
__device__ __forceinline__ void bar_wg(int wg) { asm volatile("bar.sync %0, 128;" :: "r"(2 + wg) : "memory"); }
__device__ __forceinline__ void cluster_sync() {
  asm volatile("barrier.cluster.arrive.relaxed.aligned;\nbarrier.cluster.wait.aligned;" ::: "memory");
}
__device__ __forceinline__ void cluster_wait() { asm volatile("barrier.cluster.wait.acquire.aligned;" ::: "memory"); }
enum { BAR_KV = 4  , BAR_O = 7  , BAR_WF = 12  , BAR_SKEW = 13 };

__device__ __forceinline__ void wgmma_fence() { asm volatile("wgmma.fence.sync.aligned;" ::: "memory"); }
__device__ __forceinline__ void wgmma_commit() { asm volatile("wgmma.commit_group.sync.aligned;" ::: "memory"); }
template <int N> __device__ __forceinline__ void wgmma_wait() { asm volatile("wgmma.wait_group.sync.aligned %0;" :: "n"(N) : "memory"); }

template <int scale_d, int tnsp_b = 1> __device__ __forceinline__ void wgmma_n192(float* d, uint64_t descA, uint64_t descB) {
  asm volatile("{\n.reg .pred p;\nsetp.ne.b32 p, %98, 0;\n"
               "wgmma.mma_async.sync.aligned.m64n192k16.f32.bf16.bf16 {%0,%1,%2,%3,%4,%5,%6,%7,%8,%9,%10,%11,%12,%13,%14,%15,%16,%17,%18,%19,%20,%21,%22,%23,%24,%25,%26,%27,%28,%29,%30,%31,%32,%33,%34,%35,%36,%37,%38,%39,%40,%41,%42,%43,%44,%45,%46,%47,%48,%49,%50,%51,%52,%53,%54,%55,%56,%57,%58,%59,%60,%61,%62,%63,%64,%65,%66,%67,%68,%69,%70,%71,%72,%73,%74,%75,%76,%77,%78,%79,%80,%81,%82,%83,%84,%85,%86,%87,%88,%89,%90,%91,%92,%93,%94,%95}, %96, %97, p, 1, 1, 0, %99;\n}\n"
               : "+f"(d[0]), "+f"(d[1]), "+f"(d[2]), "+f"(d[3]), "+f"(d[4]), "+f"(d[5]), "+f"(d[6]), "+f"(d[7]), "+f"(d[8]), "+f"(d[9]), "+f"(d[10]), "+f"(d[11]), "+f"(d[12]), "+f"(d[13]), "+f"(d[14]), "+f"(d[15]), "+f"(d[16]), "+f"(d[17]), "+f"(d[18]), "+f"(d[19]), "+f"(d[20]), "+f"(d[21]), "+f"(d[22]), "+f"(d[23]), "+f"(d[24]), "+f"(d[25]), "+f"(d[26]), "+f"(d[27]), "+f"(d[28]), "+f"(d[29]), "+f"(d[30]), "+f"(d[31]), "+f"(d[32]), "+f"(d[33]), "+f"(d[34]), "+f"(d[35]), "+f"(d[36]), "+f"(d[37]), "+f"(d[38]), "+f"(d[39]), "+f"(d[40]), "+f"(d[41]), "+f"(d[42]), "+f"(d[43]), "+f"(d[44]), "+f"(d[45]), "+f"(d[46]), "+f"(d[47]), "+f"(d[48]), "+f"(d[49]), "+f"(d[50]), "+f"(d[51]), "+f"(d[52]), "+f"(d[53]), "+f"(d[54]), "+f"(d[55]), "+f"(d[56]), "+f"(d[57]), "+f"(d[58]), "+f"(d[59]), "+f"(d[60]), "+f"(d[61]), "+f"(d[62]), "+f"(d[63]), "+f"(d[64]), "+f"(d[65]), "+f"(d[66]), "+f"(d[67]), "+f"(d[68]), "+f"(d[69]), "+f"(d[70]), "+f"(d[71]), "+f"(d[72]), "+f"(d[73]), "+f"(d[74]), "+f"(d[75]), "+f"(d[76]), "+f"(d[77]), "+f"(d[78]), "+f"(d[79]), "+f"(d[80]), "+f"(d[81]), "+f"(d[82]), "+f"(d[83]), "+f"(d[84]), "+f"(d[85]), "+f"(d[86]), "+f"(d[87]), "+f"(d[88]), "+f"(d[89]), "+f"(d[90]), "+f"(d[91]), "+f"(d[92]), "+f"(d[93]), "+f"(d[94]), "+f"(d[95])
               : "l"(descA), "l"(descB), "n"(scale_d), "n"(tnsp_b));
}
template <int scale_d> __device__ __forceinline__ void wgmma4_n192(float* d, uint32_t da, uint32_t db) {
#define R_ "{%0,%1,%2,%3,%4,%5,%6,%7,%8,%9,%10,%11,%12,%13,%14,%15,%16,%17,%18,%19,%20,%21,%22,%23,%24,%25,%26,%27,%28,%29,%30,%31,%32,%33,%34,%35,%36,%37,%38,%39,%40,%41,%42,%43,%44,%45,%46,%47,%48,%49,%50,%51,%52,%53,%54,%55,%56,%57,%58,%59,%60,%61,%62,%63,%64,%65,%66,%67,%68,%69,%70,%71,%72,%73,%74,%75,%76,%77,%78,%79,%80,%81,%82,%83,%84,%85,%86,%87,%88,%89,%90,%91,%92,%93,%94,%95}"
  asm volatile("{\n.reg .pred p, q;\n.reg .b64 a, b;\nsetp.ne.b32 p, %98, 0;\nsetp.eq.b32 q, 0, 0;\nmov.b64 a, {%96, 0x40000040};\nmov.b64 b, {%97, 0x40000040};\n"
               "wgmma.mma_async.sync.aligned.m64n192k16.f32.bf16.bf16 " R_ ", a, b, p, 1, 1, 0, 1;\nadd.s64 a, a, 2;\nadd.s64 b, b, 128;\n"
               "wgmma.mma_async.sync.aligned.m64n192k16.f32.bf16.bf16 " R_ ", a, b, q, 1, 1, 0, 1;\nadd.s64 a, a, 2;\nadd.s64 b, b, 128;\n"
               "wgmma.mma_async.sync.aligned.m64n192k16.f32.bf16.bf16 " R_ ", a, b, q, 1, 1, 0, 1;\nadd.s64 a, a, 2;\nadd.s64 b, b, 128;\n"
               "wgmma.mma_async.sync.aligned.m64n192k16.f32.bf16.bf16 " R_ ", a, b, q, 1, 1, 0, 1;\n}\n"
               : "+f"(d[0]), "+f"(d[1]), "+f"(d[2]), "+f"(d[3]), "+f"(d[4]), "+f"(d[5]), "+f"(d[6]), "+f"(d[7]), "+f"(d[8]), "+f"(d[9]), "+f"(d[10]), "+f"(d[11]), "+f"(d[12]), "+f"(d[13]), "+f"(d[14]), "+f"(d[15]), "+f"(d[16]), "+f"(d[17]), "+f"(d[18]), "+f"(d[19]), "+f"(d[20]), "+f"(d[21]), "+f"(d[22]), "+f"(d[23]), "+f"(d[24]), "+f"(d[25]), "+f"(d[26]), "+f"(d[27]), "+f"(d[28]), "+f"(d[29]), "+f"(d[30]), "+f"(d[31]), "+f"(d[32]), "+f"(d[33]), "+f"(d[34]), "+f"(d[35]), "+f"(d[36]), "+f"(d[37]), "+f"(d[38]), "+f"(d[39]), "+f"(d[40]), "+f"(d[41]), "+f"(d[42]), "+f"(d[43]), "+f"(d[44]), "+f"(d[45]), "+f"(d[46]), "+f"(d[47]), "+f"(d[48]), "+f"(d[49]), "+f"(d[50]), "+f"(d[51]), "+f"(d[52]), "+f"(d[53]), "+f"(d[54]), "+f"(d[55]), "+f"(d[56]), "+f"(d[57]), "+f"(d[58]), "+f"(d[59]), "+f"(d[60]), "+f"(d[61]), "+f"(d[62]), "+f"(d[63]), "+f"(d[64]), "+f"(d[65]), "+f"(d[66]), "+f"(d[67]), "+f"(d[68]), "+f"(d[69]), "+f"(d[70]), "+f"(d[71]), "+f"(d[72]), "+f"(d[73]), "+f"(d[74]), "+f"(d[75]), "+f"(d[76]), "+f"(d[77]), "+f"(d[78]), "+f"(d[79]), "+f"(d[80]), "+f"(d[81]), "+f"(d[82]), "+f"(d[83]), "+f"(d[84]), "+f"(d[85]), "+f"(d[86]), "+f"(d[87]), "+f"(d[88]), "+f"(d[89]), "+f"(d[90]), "+f"(d[91]), "+f"(d[92]), "+f"(d[93]), "+f"(d[94]), "+f"(d[95])
               : "r"(da), "r"(db), "n"(scale_d));
#undef R_
}
template <int scale_d> __device__ __forceinline__ void wgmma4_n128(float* d, uint32_t da, uint32_t db) {
#define R_ "{%0,%1,%2,%3,%4,%5,%6,%7,%8,%9,%10,%11,%12,%13,%14,%15,%16,%17,%18,%19,%20,%21,%22,%23,%24,%25,%26,%27,%28,%29,%30,%31,%32,%33,%34,%35,%36,%37,%38,%39,%40,%41,%42,%43,%44,%45,%46,%47,%48,%49,%50,%51,%52,%53,%54,%55,%56,%57,%58,%59,%60,%61,%62,%63}"
  asm volatile("{\n.reg .pred p, q;\n.reg .b64 a, b;\nsetp.ne.b32 p, %66, 0;\nsetp.eq.b32 q, 0, 0;\nmov.b64 a, {%64, 0x40000040};\nmov.b64 b, {%65, 0x40000040};\n"
               "wgmma.mma_async.sync.aligned.m64n128k16.f32.bf16.bf16 " R_ ", a, b, p, 1, 1, 0, 1;\nadd.s64 a, a, 2;\nadd.s64 b, b, 128;\n"
               "wgmma.mma_async.sync.aligned.m64n128k16.f32.bf16.bf16 " R_ ", a, b, q, 1, 1, 0, 1;\nadd.s64 a, a, 2;\nadd.s64 b, b, 128;\n"
               "wgmma.mma_async.sync.aligned.m64n128k16.f32.bf16.bf16 " R_ ", a, b, q, 1, 1, 0, 1;\nadd.s64 a, a, 2;\nadd.s64 b, b, 128;\n"
               "wgmma.mma_async.sync.aligned.m64n128k16.f32.bf16.bf16 " R_ ", a, b, q, 1, 1, 0, 1;\n}\n"
               : "+f"(d[0]), "+f"(d[1]), "+f"(d[2]), "+f"(d[3]), "+f"(d[4]), "+f"(d[5]), "+f"(d[6]), "+f"(d[7]), "+f"(d[8]), "+f"(d[9]), "+f"(d[10]), "+f"(d[11]), "+f"(d[12]), "+f"(d[13]), "+f"(d[14]), "+f"(d[15]), "+f"(d[16]), "+f"(d[17]), "+f"(d[18]), "+f"(d[19]), "+f"(d[20]), "+f"(d[21]), "+f"(d[22]), "+f"(d[23]), "+f"(d[24]), "+f"(d[25]), "+f"(d[26]), "+f"(d[27]), "+f"(d[28]), "+f"(d[29]), "+f"(d[30]), "+f"(d[31]), "+f"(d[32]), "+f"(d[33]), "+f"(d[34]), "+f"(d[35]), "+f"(d[36]), "+f"(d[37]), "+f"(d[38]), "+f"(d[39]), "+f"(d[40]), "+f"(d[41]), "+f"(d[42]), "+f"(d[43]), "+f"(d[44]), "+f"(d[45]), "+f"(d[46]), "+f"(d[47]), "+f"(d[48]), "+f"(d[49]), "+f"(d[50]), "+f"(d[51]), "+f"(d[52]), "+f"(d[53]), "+f"(d[54]), "+f"(d[55]), "+f"(d[56]), "+f"(d[57]), "+f"(d[58]), "+f"(d[59]), "+f"(d[60]), "+f"(d[61]), "+f"(d[62]), "+f"(d[63])
               : "r"(da), "r"(db), "n"(scale_d));
#undef R_
}
template <int scale_d> __device__ __forceinline__ void wgmma_n32(float* d, uint64_t descA, uint64_t descB) {
  asm volatile("{\n.reg .pred p;\nsetp.ne.b32 p, %18, 0;\n"
               "wgmma.mma_async.sync.aligned.m64n32k16.f32.bf16.bf16 {%0,%1,%2,%3,%4,%5,%6,%7,%8,%9,%10,%11,%12,%13,%14,%15}, %16, %17, p, 1, 1, 0, 1;\n}\n"
               : "+f"(d[0]), "+f"(d[1]), "+f"(d[2]), "+f"(d[3]), "+f"(d[4]), "+f"(d[5]), "+f"(d[6]), "+f"(d[7]), "+f"(d[8]), "+f"(d[9]), "+f"(d[10]), "+f"(d[11]), "+f"(d[12]), "+f"(d[13]), "+f"(d[14]), "+f"(d[15])
               : "l"(descA), "l"(descB), "n"(scale_d));
}
template <int scale_d, int tnsp_a> __device__ __forceinline__ void wgmma_n40(float* d, uint64_t descA, uint64_t descB) {
  asm volatile("{\n.reg .pred p;\nsetp.ne.b32 p, %22, 0;\n"
               "wgmma.mma_async.sync.aligned.m64n40k16.f32.bf16.bf16 {%0,%1,%2,%3,%4,%5,%6,%7,%8,%9,%10,%11,%12,%13,%14,%15,%16,%17,%18,%19}, %20, %21, p, 1, 1, %23, 1;\n}\n"
               : "+f"(d[0]), "+f"(d[1]), "+f"(d[2]), "+f"(d[3]), "+f"(d[4]), "+f"(d[5]), "+f"(d[6]), "+f"(d[7]), "+f"(d[8]), "+f"(d[9]), "+f"(d[10]), "+f"(d[11]), "+f"(d[12]), "+f"(d[13]), "+f"(d[14]), "+f"(d[15]), "+f"(d[16]), "+f"(d[17]), "+f"(d[18]), "+f"(d[19])
               : "l"(descA), "l"(descB), "n"(scale_d), "n"(tnsp_a));
}
template <int scale_d> __device__ __forceinline__ void wgmma_n40_rs(float* d, const uint32_t* a, uint64_t descB) {
  asm volatile("{\n.reg .pred p;\nsetp.ne.b32 p, %25, 0;\n"
               "wgmma.mma_async.sync.aligned.m64n40k16.f32.bf16.bf16 {%0,%1,%2,%3,%4,%5,%6,%7,%8,%9,%10,%11,%12,%13,%14,%15,%16,%17,%18,%19}, {%20,%21,%22,%23}, %24, p, 1, 1, 1;\n}\n"
               : "+f"(d[0]), "+f"(d[1]), "+f"(d[2]), "+f"(d[3]), "+f"(d[4]), "+f"(d[5]), "+f"(d[6]), "+f"(d[7]), "+f"(d[8]), "+f"(d[9]), "+f"(d[10]), "+f"(d[11]), "+f"(d[12]), "+f"(d[13]), "+f"(d[14]), "+f"(d[15]), "+f"(d[16]), "+f"(d[17]), "+f"(d[18]), "+f"(d[19])
               : "r"(a[0]), "r"(a[1]), "r"(a[2]), "r"(a[3]), "l"(descB), "n"(scale_d));
}
__device__ __forceinline__ uint64_t make_desc(uint32_t addr, uint32_t lbo_bytes, uint32_t sbo_bytes) {
  return (uint64_t)((addr & 0x3FFFF) >> 4) | ((uint64_t)(lbo_bytes >> 4) << 16) | ((uint64_t)(sbo_bytes >> 4) << 32) | (1ull << 62);
}

__device__ __forceinline__ void ldsm_x4(uint32_t addr, uint32_t& r0, uint32_t& r1, uint32_t& r2, uint32_t& r3) {
  asm volatile("ldmatrix.sync.aligned.m8n8.x4.shared.b16 {%0,%1,%2,%3}, [%4];" : "=r"(r0), "=r"(r1), "=r"(r2), "=r"(r3) : "r"(addr) : "memory");
}
__device__ __forceinline__ void ldsm_x4_t(uint32_t addr, uint32_t& r0, uint32_t& r1, uint32_t& r2, uint32_t& r3) {
  asm volatile("ldmatrix.sync.aligned.m8n8.x4.trans.shared.b16 {%0,%1,%2,%3}, [%4];" : "=r"(r0), "=r"(r1), "=r"(r2), "=r"(r3) : "r"(addr) : "memory");
}
__device__ __forceinline__ void stsm_x4(uint32_t addr, uint32_t r0, uint32_t r1, uint32_t r2, uint32_t r3) {
  asm volatile("stmatrix.sync.aligned.m8n8.x4.shared.b16 [%0], {%1,%2,%3,%4};" :: "r"(addr), "r"(r0), "r"(r1), "r"(r2), "r"(r3) : "memory");
}
__device__ __forceinline__ void sts128(uint32_t addr, uint32_t a, uint32_t b, uint32_t c, uint32_t d) {
  asm volatile("st.shared.v4.u32 [%0], {%1,%2,%3,%4};" :: "r"(addr), "r"(a), "r"(b), "r"(c), "r"(d) : "memory");
}
__device__ __forceinline__ float lds32f(uint32_t addr) {
  float v;
  asm volatile("ld.shared.f32 %0, [%1];" : "=f"(v) : "r"(addr) : "memory");
  return v;
}
__device__ __forceinline__ void sts32f(uint32_t addr, float a) {
  asm volatile("st.shared.f32 [%0], %1;" :: "r"(addr), "f"(a) : "memory");
}
__device__ __forceinline__ void mma_bf16(float (&c)[4], uint32_t a0, uint32_t a1, uint32_t a2, uint32_t a3, uint32_t b0, uint32_t b1) {
  asm volatile("mma.sync.aligned.m16n8k16.row.col.f32.bf16.bf16.f32 {%0,%1,%2,%3}, {%4,%5,%6,%7}, {%8,%9}, {%0,%1,%2,%3};"
               : "+f"(c[0]), "+f"(c[1]), "+f"(c[2]), "+f"(c[3]) : "r"(a0), "r"(a1), "r"(a2), "r"(a3), "r"(b0), "r"(b1));
}
__device__ __forceinline__ uint32_t pack_bf16(float lo, float hi) {
  uint32_t r;
  asm("cvt.rn.bf16x2.f32 %0, %1, %2;" : "=r"(r) : "f"(hi), "f"(lo));
  return r;
}
__device__ __forceinline__ float bf_lo(uint32_t v) { return __uint_as_float(v << 16); }
__device__ __forceinline__ float bf_hi(uint32_t v) { return __uint_as_float(v & 0xFFFF0000u); }
__device__ __forceinline__ void split3(float x, uint32_t& h, uint32_t& m, uint32_t& l) {
  h = pack_bf16(x, 0.f); x -= bf_lo(h);
  m = pack_bf16(x, 0.f); x -= bf_lo(m);
  l = pack_bf16(x, 0.f);
}
__device__ __forceinline__ float ex2(float x) { float r; asm("ex2.approx.ftz.f32 %0, %1;" : "=f"(r) : "f"(x)); return r; }
__device__ __forceinline__ float rcp_fast(float x) { float r; asm("rcp.approx.ftz.f32 %0, %1;" : "=f"(r) : "f"(x)); return r; }
__device__ __forceinline__ void red_v4(float* p, float a, float b, float c, float d) {
  asm volatile("red.global.add.v4.f32 [%0], {%1, %2, %3, %4};" :: "l"(p), "f"(a), "f"(b), "f"(c), "f"(d) : "memory");
}
__device__ __forceinline__ uint4 ld_ll(const uint4* p) {
  uint4 v;
  asm volatile("{\n.reg .b64 a, b;\nld.relaxed.gpu.global.v2.b64 {a, b}, [%4];\nmov.b64 {%0, %1}, a;\nmov.b64 {%2, %3}, b;\n}\n"
               : "=r"(v.x), "=r"(v.y), "=r"(v.z), "=r"(v.w) : "l"(p) : "memory");
  return v;
}
__device__ __forceinline__ void st_b64(uint2* p, uint32_t a, uint32_t b) {
  asm volatile("{\n.reg .b64 v;\nmov.b64 v, {%1, %2};\nst.relaxed.gpu.global.b64 [%0], v;\n}\n" :: "l"(p), "r"(a), "r"(b) : "memory");
}
__device__ __forceinline__ void st_b128(uint4* p, uint32_t a, uint32_t b, uint32_t c, uint32_t d) {
  asm volatile("{\n.reg .b128 v;\nmov.b128 v, {%1, %2, %3, %4};\nst.relaxed.gpu.global.b128 [%0], v;\n}\n" :: "l"(p), "r"(a), "r"(b), "r"(c), "r"(d) : "memory");
}
__device__ __forceinline__ uint4 ld_b128(const uint4* p) {
  uint4 v;
  asm volatile("{\n.reg .b128 v;\nld.relaxed.gpu.global.b128 v, [%4];\nmov.b128 {%0, %1, %2, %3}, v;\n}\n" : "=r"(v.x), "=r"(v.y), "=r"(v.z), "=r"(v.w) : "l"(p) : "memory");
  return v;
}

constexpr float LOG2E = 1.4426950408889634f;

struct Params {
  const __nv_bfloat16* x0;
  const __nv_bfloat16* wA_qkv;
  const __nv_bfloat16* wA_o;
  const __nv_bfloat16* wB_qkv;
  const __nv_bfloat16* wB_phi;
  const __nv_bfloat16* wB_o;
  __nv_bfloat16* out;
};

#define ACC_DEF(d, n) _Pragma("unroll") for (int i_ = 0; i_ < (n); i_++) asm volatile("" : "=f"(d[i_]))
#define ACC_FENCE(d, n) _Pragma("unroll") for (int i_ = 0; i_ < (n); i_++) asm volatile("" : "+f"(d[i_]) :: "memory")
#define PIN(a, n) _Pragma("unroll") for (int i_ = 0; i_ < (n); i_++) asm volatile("" : "+f"((a)[i_]))
#define PINU(a, n) _Pragma("unroll") for (int i_ = 0; i_ < (n); i_++) asm volatile("" : "+r"((a)[i_]))

#define STAGE64(acc, off, p0, KIND, SEND) { \
    uint32_t w_[4][4]; \
    _Pragma("unroll") for (int j_ = 0; j_ < 4; j_++) { \
      const int o_ = (off) + j_ * 8; \
      w_[j_][0] = pack_bf16(rs0 * acc[o_ + 0], rs0 * acc[o_ + 1]); \
      w_[j_][1] = pack_bf16(rs1 * acc[o_ + 2], rs1 * acc[o_ + 3]); \
      w_[j_][2] = pack_bf16(rs0 * acc[o_ + 4], rs0 * acc[o_ + 5]); \
      w_[j_][3] = pack_bf16(rs1 * acc[o_ + 6], rs1 * acc[o_ + 7]); \
    } \
    if ((SEND) && hsend) { \
      _Pragma("unroll") for (int j_ = 0; j_ < 4; j_++) { \
        w_[j_][0] = (w_[j_][0] & ~1u) | hbit; \
        st_b128(hbase + lane + ((KIND) * 4 + j_) * 32, w_[j_][0], w_[j_][1], w_[j_][2], w_[j_][3]); \
      } \
    } \
    _Pragma("unroll") for (int j_ = 0; j_ < 4; j_++) \
      stsm_x4((KIND) ? (p0) + (j_ >> 1) * 8192 + (srowoff >> 1) + ((((uint32_t)(j_ & 1) << 5) + lhi) ^ lsw2) \
                     : (p0) + srowoff + ((((uint32_t)j_ << 5) + lhi) ^ lsw), \
              w_[j_][0], w_[j_][1], w_[j_][2], w_[j_][3]); \
  }
#define RW(j) (((j) >> 1) * 4 + ((j) & 1))
__device__ __forceinline__ float rmax16(const float* p) {
  float m[4];
#pragma unroll
  for (int j = 0; j < 4; j++) m[j] = fmaxf(fmaxf(p[RW(j)], p[RW(j + 4)]), fmaxf(p[RW(j + 8)], p[RW(j + 12)]));
  const float r = fmaxf(fmaxf(m[0], m[1]), fmaxf(m[2], m[3]));
  return fmaxf(r, __shfl_xor_sync(0xffffffffu, r, 1));
}
__device__ __forceinline__ float rmin16(const float* p) {
  float m[4];
#pragma unroll
  for (int j = 0; j < 4; j++) m[j] = fminf(fminf(p[RW(j)], p[RW(j + 4)]), fminf(p[RW(j + 8)], p[RW(j + 12)]));
  const float r = fminf(fminf(m[0], m[1]), fminf(m[2], m[3]));
  return fminf(r, __shfl_xor_sync(0xffffffffu, r, 1));
}
__device__ __forceinline__ float exps16(float* o, const float* p, float c, float b) {
  float s[4];
#pragma unroll
  for (int j = 0; j < 16; j++) { o[j] = ex2(fmaf(p[RW(j)], c, b)); if (j < 4) s[j] = o[j]; else s[j & 3] += o[j]; }
  return (s[0] + s[1]) + (s[2] + s[3]);
}
__device__ __forceinline__ void store16(const float* e, float sum, uint32_t dst, uint32_t dsw, int c0) {
  const float inv = rcp_fast(sum + __shfl_xor_sync(0xffffffffu, sum, 1));
#pragma unroll
  for (int j = 0; j < 2; j++)
    sts128(dst + (((c0 + j) << 4) ^ dsw), pack_bf16(e[j * 8] * inv, e[j * 8 + 1] * inv), pack_bf16(e[j * 8 + 2] * inv, e[j * 8 + 3] * inv),
           pack_bf16(e[j * 8 + 4] * inv, e[j * 8 + 5] * inv), pack_bf16(e[j * 8 + 6] * inv, e[j * 8 + 7] * inv));
}
__device__ __forceinline__ void expp16(uint32_t* o, const float* p, float c0, float b0, float c1, float b1) {
#pragma unroll
  for (int j = 0; j < 8; j++) {
    const float c = (j & 1) ? c1 : c0, b = (j & 1) ? b1 : b0;
    o[j] = pack_bf16(ex2(fmaf(p[2 * j], c, b)), ex2(fmaf(p[2 * j + 1], c, b)));
  }
}
__device__ __forceinline__ void extrema(float* m, const float* p, float c0, float c1) {
#pragma unroll
  for (int i = 0; i < 4; i++) {
    const float* q = p + (i >> 1) * 16 + (i & 1) * 2;
    m[(i >> 1) * 4 + (i & 1)] = fminf(fminf(fminf(q[0], q[1]), fminf(q[4], q[5])), fminf(fminf(q[8], q[9]), fminf(q[12], q[13])));
    m[(i >> 1) * 4 + (i & 1) + 2] = fmaxf(fmaxf(fmaxf(q[0], q[1]), fmaxf(q[4], q[5])), fmaxf(fmaxf(q[8], q[9]), fmaxf(q[12], q[13])));
  }
#pragma unroll
  for (int o = 1; o <= 2; o <<= 1)
#pragma unroll
    for (int i = 0; i < 8; i++) { const float x = __shfl_xor_sync(0xffffffffu, m[i], o); m[i] = (i & 2) ? fmaxf(m[i], x) : fminf(m[i], x); }
#pragma unroll
  for (int i = 0; i < 8; i++) m[i] *= ((i & 2) ? -1.f : 1.f) * ((i & 1) ? c1 : c0);
}
#define SCHED_FENCE() asm volatile("pmevent 0;" ::: "memory")

__global__ void __cluster_dims__(2, 1, 1) __launch_bounds__(384, 1)
mega_kernel(const __grid_constant__ CUtensorMap tm_x0, const __grid_constant__ CUtensorMap tm_xo, const __grid_constant__ CUtensorMap tm_os,
            const __grid_constant__ CUtensorMap tm_o, const __grid_constant__ CUtensorMap tm_wf,
            const __grid_constant__ CUtensorMap tm_wqA, const __grid_constant__ CUtensorMap tm_wqB,
            const __grid_constant__ CUtensorMap tm_woA, const __grid_constant__ CUtensorMap tm_woB,
            const __grid_constant__ CUtensorMap tm_phi, const Params prm) {
  extern __shared__ __align__(1024) uint8_t smem_raw[];
  const uint32_t sbase = smem_u32(smem_raw);
  const uint32_t bar_full = sbase + OFF_BAR;
  const uint32_t bar_done = bar_full + 384;
  const uint32_t bar_stat = bar_full + 768, bar_stat2 = bar_full + 776, bar_epi = bar_full + 784, bar_phi = bar_full + 936  ;
  const uint32_t bar_xr = bar_full + 800, bar_lx = bar_full + 808, bar_kvf = bar_full + 816  , bar_stg = bar_full + 832;
  const uint32_t bar_chk = bar_full + 848;

  const int warp = __shfl_sync(0xffffffffu, threadIdx.x >> 5, 0), lane = threadIdx.x & 31;
  uint32_t rank;
  asm volatile("mov.u32 %0, %%cluster_ctarank;" : "=r"(rank));
  const int cta = (int)blockIdx.x - NAUX;
  const int cl = cta >> 1;
  const int jj = cl & 7, cc = cl >> 3;
  const int mm = cc * 2 + (int)rank;

#define LOAD_EPOCH() const unsigned epoch = ld_relaxed(&g_flags.epoch.v), ep1 = epoch + 1; (void)epoch
  int budget = 1 << 22;

  if (cta >= 0) {
    {
      const int tx = threadIdx.x;
      const __nv_bfloat16* pf = (tx < 128) ? prm.x0 + (size_t)(mm * 128 + tx) * D_MODEL + jj * 128
                                           : prm.wA_qkv + (size_t)(jj * 128 + (tx & 63)) * 3072 + ((tx - 128) >> 6) * 1024 + jj * 128 + rank * 64;
      if (tx < 320) asm volatile("prefetch.global.L2 [%0];" :: "l"(pf));
      else if (tx == 320) prefetch_tmap(&tm_x0);
      else if (tx == 352) prefetch_tmap(&tm_wqA);
      else if (tx == 383) asm volatile("prefetch.global.L2 [%0];" :: "l"(&g_flags.epoch.v));
    }
    if (elect_one()) {
#pragma unroll
      for (int i = 0; i < 4; i++) {
        const int u = warp * 4 + i;
        mbar_init(bar_full + u * 8, ((u >= 4 && u < 11) || u > 40) ? 2 : 1); mbar_init(bar_done + u * 8, 16);
      }
      mbar_init(bar_stat + warp * 16, 0x111111181182ull >> (4 * warp) & 15);
      mbar_init(bar_stat + warp * 16 + 8, 0x111111121811ull >> (4 * warp) & 15);
      asm volatile("fence.mbarrier_init.release.cluster;" ::: "memory");
    }
    __syncthreads();
    asm volatile("barrier.cluster.arrive.relaxed.aligned;" ::: "memory");
  }

  if (cta < 0) {
    LOAD_EPOCH();
    const uint32_t buf = sbase + warp * SLOT, bar = sbase + OFF_BAR + warp * 16;
    const uint32_t lsw = (lane & 7) << 4, lhi = (lane >> 4) << 4, lrow = (lane & 15) * 128;
    const bool el = elect_one();
    if (el) {
      mbar_init(bar, 1); mbar_init(bar + 8, 1);
      asm volatile("fence.mbarrier_init.release.cluster;" ::: "memory");
    }
#pragma unroll 1
    for (int rd = 0; rd < (NLAYERS > 1 ? 5 : 2); rd++) {
      if (rd >= 2 && warp >= 8) break;
      const int tk = rd < 2 ? blockIdx.x * 12 + warp : blockIdx.x * 8 + warp;
      const int half = tk & 1;
      const int blk = rd < 2 ? (tk >> 1) * 2 + rd : (4 - rd) * 16 + (tk >> 1);
      const CUtensorMap* tm = rd < 2 ? &tm_wqA : (rd == 2 ? &tm_wqB : &tm_wf);
      const int j0 = (blk & 15) >> 1;
#define AUX_LOAD(n) { const uint32_t d_ = buf + ((n) & 1) * 8192, b_ = bar + ((n) & 1) * 8; const int r_ = kslice(j0, 2 * (n) + half) * 64; \
        mbar_expect_tx(b_, 8192); tma_load_2d(d_, tm, b_, blk * 64, r_); tma_load_2d(d_ + 4096, tm, b_, blk * 64, r_ + 32); }
      if (el) {
        if (rd == 3) { wait_flag(&g_flags.wfready[j0].v, ep1 * 16); fence_proxy_async_global(); }
        AUX_LOAD(0); AUX_LOAD(1);
      }
      __syncwarp();
      float cs[8][4];
#pragma unroll
      for (int i = 0; i < 8; i++) cs[i][0] = cs[i][1] = cs[i][2] = cs[i][3] = 0.f;
#pragma unroll 1
      for (int n = 0; n < 8; n++) {
        const uint32_t tb = buf + (n & 1) * 8192 + lrow;
        mbar_wait(bar + (n & 1) * 8, (n >> 1) & 1);
#pragma unroll
        for (int i = 0; i < 16; i++) {
          uint32_t b0, b1, b2, b3;
          ldsm_x4_t(tb + (i >> 2) * 2048 + (((i & 3) * 32 + lhi) ^ lsw), b0, b1, b2, b3);
          mma_bf16(cs[2 * (i & 3)], 0x3F803F80u, 0x3F803F80u, 0x3F803F80u, 0x3F803F80u, b0, b1);
          mma_bf16(cs[2 * (i & 3) + 1], 0x3F803F80u, 0x3F803F80u, 0x3F803F80u, 0x3F803F80u, b2, b3);
        }
        __syncwarp();
        if (el && n < 6) AUX_LOAD(n + 2);
        __syncwarp();
      }
      if (lane < 4) {
#pragma unroll
        for (int i = 0; i < 8; i++) st_b64(&g_colsum[rd >= 2][blk * 32 + i * 4 + lane][half], __float_as_uint(cs[i][0]), (__float_as_uint(cs[i][1]) & ~3u) | (ep1 & 3));
      }
      __syncwarp();
    }
  } else if (warp >= 8) {
    asm volatile("setmaxnreg.dec.sync.aligned.u32 40;");
    if (warp == 8) {
      const bool el = elect_one();
      cluster_wait();
      if (el) {
#pragma unroll 1
        for (int l = 0; l < NLAYERS; l++) {
          const uint32_t par = l & 1;
          const CUtensorMap* tqk = par ? &tm_wf : &tm_wqA;
          const CUtensorMap* tv = par ? &tm_wqB : &tm_wqA;
          const CUtensorMap* two = par ? &tm_woB : &tm_woA;
          if (l == 1) { LOAD_EPOCH(); wait_flag(&g_flags.wfready[jj].v, ep1 * 16); fence_proxy_async_global(); }
#pragma unroll 1
          for (int u = 0; u < 32; u++) {
            if (u >= 4) mbar_wait_sl(bar_done + (u - 4) * 8, par);
            else if (l) mbar_wait_sl(bar_done + (43 + u + (u >> 1)) * 8, par ^ 1);
            else if (u == 1) __nanosleep(STAG1);
            else if (u == 2) mbar_wait_sl(bar_full, 0);
            const uint32_t fb = bar_full + u * 8;
            const bool res = u < 4 ? (l || u >= 2) : (u < 11 || (u >= 18 && u < 22));
            mbar_expect_tx(fb, res ? QST : QST + SLOT);
            const int row = kslice(jj, u < 4 ? u & 1 : (u < 18 ? u - 2 : (u < 22 ? u - 6 : u - 20))) * 64 + (int)rank * 32;
            const int ps = u < 4 ? u >> 1 : (u >= 18), col = jj * 128 + ps * 64;
            const int c0 = par ? jj * 128 + (ps ? 0 : 1024) : col;
            const uint32_t dst = sbase + (u & 3) * QST + rank * 4096;
            tma_load_2d_mc(dst, tqk, fb, c0, row);
            tma_load_2d_mc(dst + 8192, tqk, fb, c0 + (par ? 64 : 1024), row);
            tma_load_2d_mc(dst + 16384, tv, fb, col + 2048, row);
            if (l == 0 && u < 4) PROFT(473 + u);
          }
#pragma unroll 1
          for (int s = 0; s < 16; s++) {
            if (s < 5) { if (s != 2 && s != 4) mbar_wait_sl(bar_done + (28 + s) * 8, par); }
            else if (s != 14) mbar_wait_sl(bar_done + (27 + s - (s == 15)) * 8, par);
            const uint32_t fb = bar_full + (32 + s) * 8;
            mbar_expect_tx(fb, (s && s < 8) ? 2 * SLOT : SLOT);
            tma_load_2d_mc(sbase + rank * 8192 + (uint32_t)((WO_BSLOT >> (4 * s)) & 15) * SLOT, two, fb, jj * 128 + (int)rank * 64, wslice(jj, s) * 64);
            if (s >= 5 && s < 8) {
              if (s == 5) { mbar_wait_sl(bar_full + 33 * 8, par); fence_proxy_async_global(); }
              tma_load_2d(sbase + (uint32_t)((WO_ASLOT(par) >> (4 * s)) & 15) * SLOT, &tm_o, fb, wslice(jj, s) * 64, mm * 128);
            }
          }
        }
      }
      __syncwarp();
    } else if (warp == 9) {
      const bool el = elect_one();
      if (el) {
        PROFT(472);
        tma_load_2d(sbase + OFF_S, &tm_x0, bar_full, jj * 128, mm * 128);
        __nanosleep(STAG1);
        tma_load_2d(sbase + OFF_S + SLOT, &tm_x0, bar_full + 8, jj * 128 + 64, mm * 128);
      }
      __syncwarp();
      LOAD_EPOCH();
#pragma unroll 1
      for (int lp = 0; lp < 2 * NLAYERS; lp++) {
        const int l = lp >> 1, ph = lp & 1;
        const uint32_t par = l & 1;
        const __nv_bfloat16* pb = g_obuf + ph * 64 + (size_t)(mm * 128 + (ph ? 0 : S_LEN) + (lane & 7) * 16 + (jj & 1) * 8) * D_MODEL + (jj >> 1) * 16;
        const CUtensorMap* tm = lp ? &tm_o : &tm_x0;
        const int row = mm * 128 + ((ph || !l) ? 0 : S_LEN);
        const uint32_t bit = ph ? O_BIT(l) : X_BIT(l - 1);
        const uint32_t slots = ph ? (uint32_t)(WO_ASLOT(par) >> 36) : 0x8769876u;
        uint32_t rdy = lp ? 0 : 0xFF;
        mbar_wait_sl(ph ? bar_epi : (l ? bar_done + 47 * 8 : bar_full), ph ? par : (l ? par ^ 1 : 0));
#pragma unroll 1
        for (int i = 0; i < 7; i++) {
          if (!((rdy >> i) & 1)) {
            const unsigned* pp = reinterpret_cast<const unsigned*>(pb + ((jj + i + 1 + ((lane >> 3) & (POLLW - 1))) & 7) * 128);
            if (i == 0) __nanosleep(POLL0);
            unsigned v0 = ld_relaxed(pp);
            __nanosleep(POLLGAP);
            unsigned v1 = ld_relaxed(pp);
            uint32_t no;
#pragma unroll 1
            for (int it = 0; it < (1 << 18); it++) {
              no = __ballot_sync(0xffffffffu, (v0 ^ bit) & 1);
              if (!(no & 0xFF)) break;
              v0 = ld_relaxed(pp);
              no = __ballot_sync(0xffffffffu, (v1 ^ bit) & 1);
              if (!(no & 0xFF)) break;
              v1 = ld_relaxed(pp);
            }
            rdy = ((1 | (no & 0xFF00 ? 0 : 2) | (no & 0xFF0000 ? 0 : 4) | (no >> 24 ? 0 : 8)) & ((1 << POLLW) - 1)) << i;
          }
          if (i >= (ph ? 2 : 4)) mbar_wait_sl(bar_done + (i + (ph ? 33 : 0)) * 8, par);
          if (el) {
            if (i == 0) PROFT(320 + l * 16 + ph * 2);
            mbar_expect_tx(bar_chk + i * 8, SLOT);
            tma_load_2d(sbase + ((slots >> (4 * i)) & 15) * SLOT, tm, bar_chk + i * 8, ((jj + i + 1) & 7) * 128 + ph * 64, row);
          }
          __syncwarp();
        }
        if (ph == 0 && el) {
          if (l) { wait_flag(&g_flags.xready[l][mm].v, ep1 * 8); fence_proxy_async_global(); }
#pragma unroll 1
          for (int u = 11; u < 34; u++) {
            if (u == 18) u = 22;
            mbar_wait_sl(bar_done + (u - 4) * 8, par);
            if (u == 32) mbar_expect_tx(bar_xr, 2 * SLOT);
            tma_load_2d(sbase + OFF_RA + (u & 3) * SLOT, tm, u < 32 ? bar_full + u * 8 : bar_xr, kslice(jj, u < 18 ? u - 2 : (u < 32 ? u - 20 : u - 32)) * 64, row);
            if (l == 0 && u < 16 && NLAYERS > 1) {
              if (u == 11) { mbar_expect_tx(bar_phi, SLOT + 8192); tma_load_2d(sbase + OFF_PHI, &tm_phi, bar_phi, 0, jj * 128); }
              else tma_load_2d(sbase + 12 * SLOT + (u - 12) * 4096, &tm_wqB, bar_phi, jj * 128 + ((u - 12) >> 1) * 64, mm * 64 + (u & 1) * 32);
            }
          }
          wait_flag(&g_flags.oready[l][mm].v, ep1 * 8);
          fence_proxy_async_global();
          PROFT(321 + l * 16);
#pragma unroll 1
          for (int s = 1; s < 5; s++) {
            if (s < 3 || s == 3 + par) mbar_wait_sl(s < 3 ? bar_done + (29 + s) * 8 : bar_lx, par);
            tma_load_2d(sbase + (uint32_t)((WO_ASLOT(par) >> (4 * s)) & 15) * SLOT, &tm_o, bar_full + (32 + s) * 8, wslice(jj, s) * 64, mm * 128);
          }
        }
        __syncwarp();
      }
      cluster_wait();
    } else {
      const int hw = warp - 10;
      LOAD_EPOCH();
      const bool el = elect_one();
      cluster_wait();
      if (hw == 0) {
        mbar_wait_sl(bar_full + 8, 0);
        if (lane < 7) prefetch_tmap(lane == 0 ? &tm_os : lane == 1 ? &tm_o : lane == 2 ? &tm_wf : lane == 3 ? &tm_wqB : lane == 4 ? &tm_woA : lane == 5 ? &tm_woB : &tm_phi);
        if (lane < 4) asm volatile("prefetch.global.L2 [%0];" :: "l"(prm.wB_phi + jj * 4096 + mm * 256 + lane * 64));
#pragma unroll 1
        for (int i = 0; i < 8; i++) {
          asm volatile("prefetch.global.L2 [%0];" :: "l"(prm.wB_qkv + (size_t)(mm * 64 + (i & 3) * 16 + (lane >> 1)) * 3072 + (i >> 2) * 1024 + jj * 128 + (lane & 1) * 64));
          __nanosleep(PFGAP);
        }
      } else {
#pragma unroll 1
        for (int b = 0; b < 2; b++) {
          float4* z = reinterpret_cast<float4*>(g_kv[b] + (jj * 4) * KVH + mm * (4 * KVH / 16)) + lane;
#pragma unroll
          for (int i = 0; i < 5; i++) z[i * 32] = make_float4(0.f, 0.f, 0.f, 0.f);
        }
#pragma unroll 1
        for (int i = 0; i < 16; i++) {
          const int b = i >> 2;
          const uint32_t v = (b == 0 ? O_BIT(0) : b == 1 ? X_BIT(0) : (NLAYERS > 2 ? 1u : ep1)) + 1;
          uint4* p = b < 2 ? reinterpret_cast<uint4*>(g_obuf + (size_t)(b * S_LEN + mm * 128 + (i & 3) * 32 + (lane >> 3) * 8) * D_MODEL + jj * 128 + (b ? 0 : 64)) + (lane & 7)
                           : g_halo + (size_t)(mm * 8 + jj) * 512 + (i - 8) * 32 + 256 + lane;
          *p = make_uint4(v, v, v, v);
        }
        fence_proxy_async_global();
      }
      __syncwarp();
      uint32_t chkp = 0;
#pragma unroll 1
      for (int lp = 0; lp < 2 * NLAYERS; lp++) {
        const int l = lp >> 1, ph = lp & 1;
        const uint32_t par = l & 1;
        int lane; asm volatile("mov.u32 %0, %%laneid;" : "=r"(lane));
        if (hw) {
          const uint32_t bit = ph ? O_BIT(l) : X_BIT(l - 1);
          const uint32_t slots = ph ? (uint32_t)(WO_ASLOT(par) >> 36) : 0x8769876u;
#pragma unroll 1
          for (int c = 0; c < 7; c++) {
            const uint32_t tile = sbase + ((slots >> (4 * c)) & 15) * SLOT;
#pragma unroll 1
            for (int it = 0; it < (1 << 12); it++) {
              mbar_wait_sl(bar_chk + c * 8, (chkp >> c) & 1);
              chkp ^= 1u << c;
              if (el && c == 0) PROFT(488 + lp);
              if (lp == 0) break;
              uint32_t a1 = 1, o1 = 0;
#pragma unroll
              for (int i = 0; i < 16; i++) {
                uint32_t w;
                asm volatile("ld.shared.u32 %0, [%1];" : "=r"(w) : "r"(tile + i * 1024 + (lane & 7) * 132 + (lane >> 3) * 32) : "memory");
                a1 &= w; o1 |= w;
              }
              if (__all_sync(0xffffffffu, ((bit ? a1 : ~o1) & 1) != 0)) break;
              if (el) {
                fence_proxy_async_smem();
                mbar_expect_tx(bar_chk + c * 8, SLOT);
                tma_load_2d(tile, &tm_o, bar_chk + c * 8, ((jj + c + 1) & 7) * 128 + ph * 64, mm * 128 + (ph ? 0 : S_LEN));
                RETRY_COUNT();
              }
              __syncwarp();
            }
            if (el) mbar_arrive_local(bar_full + (c + (ph ? 41 : 4)) * 8);
            __syncwarp();
          }
          if (ph) continue;
#pragma unroll 1
          for (int hp = 0; hp < 2; hp++) {
            const uint4* src = reinterpret_cast<const uint4*>(g_colsum[par][jj * 64 + hp * 32 + lane]);
            uint32_t bad;
            int it = 0;
            float c[6];
            do {
              bad = 0;
#pragma unroll
              for (int p = 0; p < 3; p++) {
                const uint4 v = ld_ll(src + ((par && p < 2) ? (hp ? -32 : 512) + p * 32 : p * 512));
                bad |= (v.y ^ ep1) | (v.w ^ ep1);
                c[2 * p] = __uint_as_float(v.x) + __uint_as_float(v.z); c[2 * p + 1] = __uint_as_float(v.y) + __uint_as_float(v.w);
              }
              bad &= 3;
              if (bad) __nanosleep(300);
            } while (bad && ++it < (1 << 16));
#pragma unroll
            for (int p = 0; p < 6; p++) {
              uint32_t h, m, lo;
              split3(c[p], h, m, lo);
              sts128(sbase + OFF_LNB + hp * 4096 + (p >> 1) * 1024 + lane * 32 + (p & 1) * 16, h | (m << 16), h | (lo << 16), h | (m << 16), lo | (m << 16));
            }
            fence_proxy_async_smem();
            __syncwarp();
            if (el) { mbar_arrive_local(hp ? bar_stat2 : bar_stat); if (hp == 0) PROFT(324 + l * 16); }
            __syncwarp();
          }
        } else if (ph == 0) {
          mbar_wait_sl(bar_done + 24, par);
          const uint4* sp = reinterpret_cast<const uint4*>(g_stats + (size_t)(mm * 128) * 8) + lane;
#pragma unroll 1
          for (int hf = 0; hf < 4; hf++) {
            uint4 v[4];
            uint32_t bad;
            int it = 0;
            do {
              bad = 0;
#pragma unroll
              for (int i = 0; i < 4; i++) { v[i] = ld_ll(sp + (hf * 4 + i) * 32); bad |= (v[i].y ^ STAT_TAG(l)) | (v[i].w ^ STAT_TAG(l)); }
              bad &= 3;
              if (bad) __nanosleep(200);
            } while (bad && ++it < (1 << 16));
            __syncwarp();
            float mean = 0.f, m2 = 0.f;
#pragma unroll
            for (int i = 0; i < 4; i++) {
              float a = __uint_as_float(v[i].x) + __uint_as_float(v[i].z);
              a += __shfl_xor_sync(0xffffffffu, a, 1); a += __shfl_xor_sync(0xffffffffu, a, 2);
              a *= 0.125f;
              const float e0 = __uint_as_float(v[i].x) - a, e1 = __uint_as_float(v[i].z) - a;
              float q = fmaf(fmaf(e0, e0, e1 * e1), 128.f, __uint_as_float(v[i].y) + __uint_as_float(v[i].w));
              q += __shfl_xor_sync(0xffffffffu, q, 1); q += __shfl_xor_sync(0xffffffffu, q, 2);
              if ((lane & 3) == i) { mean = a; m2 = q; }
            }
            const uint32_t row = hf * 32 + (lane & 3) * 8 + (lane >> 2);
            uint32_t h, m, lo;
            split3(-0.5f * mean, h, m, lo);
            sts128(sbase + OFF_LNA + row * 16, h | (h << 16), m | (h << 16), lo | (m << 16), m | (lo << 16));
            sts32f(sbase + OFF_ST + row * 4, rsqrtf(m2 * (1.f / 1024.f) + 1e-5f));
          }
          fence_proxy_async_smem();
          __syncwarp();
          if (el) { mbar_arrive_local(bar_stat); PROFT(323 + l * 16); }
          __syncwarp();
#pragma unroll 1
          for (int i = 0; i < 8 - 4 * l; i++) {
            asm volatile("prefetch.global.L2 [%0];" :: "l"(i < 4 ? (l ? prm.wB_o : prm.wA_o) + (size_t)cta * 8192 + i * 2048 + lane * 64
                                                                 : prm.wB_qkv + (size_t)(cta * 8 + (i - 4) * 2 + (lane >> 4)) * 3072 + 2048 + (lane & 15) * 64));
            __nanosleep(PFGAP);
          }
          continue;
        }
        if (hw) {
          if (l & 1) {
#pragma unroll 1
            for (int h = 0; h < 2; h++) {
              asm volatile("bar.sync %0, 288;" :: "r"(BAR_KV + h) : "memory");
              __syncwarp();
              PROFT(331 + l * 16 + h);
              if (lane < 16) signal_release(&g_flags.kvready[(l & 2) + h][jj][lane].v);
              const unsigned* kf = &g_flags.kvready[(l & 2) + h][jj][mm].v;
              unsigned v0 = ld_relaxed(kf);
              __nanosleep(150);
              unsigned v1 = ld_relaxed(kf);
#pragma unroll 1
              for (int it = 0; it < (1 << 18); it++) {
                if (v0 == ep1 * 16) break;
                v0 = ld_relaxed(kf);
                if (v1 == ep1 * 16) break;
                v1 = ld_relaxed(kf);
              }
              fence_acquire();
              __syncwarp();
              if (el) { mbar_arrive_local(bar_kvf + h * 8); PROFT(333 + l * 16 + h); }
              __syncwarp();
            }
          }
        } else {
#pragma unroll 1
          for (uint32_t ev = l == NLAYERS - 1 ? 0x80u : (l == 0 ? 0x836054u : 0x830u); ev != 8; ev >>= 4) {
            const int e = ev & 15;
            asm volatile("bar.sync %0, 288;" :: "r"((0xFECA987 >> (4 * e)) & 15) : "memory");
            if (el) {
              if (e < 4) {
                PROFT(325 + l * 16 + e);
                tma_store_2d(&tm_o, sbase + (e ? 11 : 12) * SLOT, jj * 128 + (e & 1) * 64, mm * 128 + (e ? S_LEN : 0));
              } else {
                if (e == 5) mbar_expect_tx(bar_phi + 8, SLOT);
#pragma unroll 1
                for (int i = 0; i < 4; i++) {
                  const uint32_t a = sbase + (e > 4 ? 10 : 12) * SLOT + i * 4096;
                  const int c0 = (e > 4 ? 1024 : 0) + jj * 128 + (i >> 1) * 64, c1 = mm * 64 + (i & 1) * 32;
                  if (e == 5) tma_load_2d(a, &tm_wqB, bar_phi + 8, c0, c1); else tma_store_2d(&tm_wf, a, c0, c1);
                }
                if (e != 5) {
                  asm volatile("cp.async.bulk.commit_group;\ncp.async.bulk.wait_group.read 0;" ::: "memory");
                  mbar_arrive_local(bar_phi + (e - 4) * 4);
                }
              }
              if ((0x49 >> e) & 1) {
                bulk_commit_wait();
                signal_release(e == 0 ? &g_flags.oready[l][mm].v : e == 6 ? &g_flags.wfready[jj].v : &g_flags.xready[l + 1][mm].v);
              }
              if (e == 3) PROFT(330 + l * 16);
              if (e == 6) PROFT(335);
            }
            __syncwarp();
          }
        }
      }
    }
    cluster_sync();
  } else {
    asm volatile("setmaxnreg.inc.sync.aligned.u32 232;");
    LOAD_EPOCH();
    const int wg = warp >> 2;
    const int r0 = warp * 16;
    const uint32_t pK = sbase + OFF_S, pV = sbase + OFF_S + SLOT;
#define PMASKS(on, bit) const uint32_t pm0 = ((on) && t == (g & 3) && (g >> 2) == (g & 1)), pm1 = ((on) && t == (g & 3) && (g >> 2) != (g & 1)), pbit = (bit)
#define PBIT0(w) (((w) & ~pm0) | (pbit & pm0))
#define PBIT1(w) (((w) & ~pm1) | (pbit & pm1))
#define LANE_CONSTS() \
    int lane; asm volatile("mov.u32 %0, %%laneid;" : "=r"(lane)); \
    const int g = lane >> 2, t = lane & 3; \
    const uint32_t srowoff = (r0 + (lane & 15)) * 128, lsw = (lane & 7) << 4, lhi = (lane >> 4) << 4, lsw2 = (lane & 6) << 3; \
    (void)g; (void)t; (void)srowoff; (void)lsw; (void)lhi; (void)lsw2;
    uint32_t stgp = 0, peer;
    asm volatile("mapa.shared::cluster.u32 %0, %1, %2;" : "=r"(peer) : "r"(sbase), "r"(rank ^ 1));
    peer -= sbase;
    const uint32_t dA0 = (((sbase & 0x3FFFF) + wg * 8192) >> 4) | 0x10000u, dB0 = ((sbase & 0x3FFFF) >> 4) | 0x2000000u;
    cluster_wait();
#define STG_ARRIVE() { __syncwarp(); if (elect_one()) mbar_arrive_local(bar_stg); }
#define STG_WAIT() { mbar_wait(bar_stg, stgp); stgp ^= 1; }
#define PROFS() do {} while (0)
#define REL(addr) { if (elect_one()) { mbar_arrive_local(addr); asm volatile("mbarrier.arrive.shared::cluster.b64 _, [%0];" :: "r"((addr) + peer) : "memory"); } }
#define QSTEP(ACC, DA, SC, PRE) { \
      const uint32_t da = (DA), db = dB0 + (ub & 0x18) * (QST >> 7); \
      mbar_wait(ub, par); \
      PRE; \
      wgmma_fence(); \
      wgmma4_n192<SC>(ACC, da, db); \
      wgmma_commit(); PROFS(); }
#define QREL() { wgmma_wait<1>(); REL(ub + 376); ub += 8; }
#define RA_CUR (dA0 + (OFF_RA >> 4) + (ub & 0x18) * (SLOT >> 7))
#define PUMP1() { QSTEP(S1, RA_CUR, 1, {}); QREL(); }
#define PUMP0() { PUMP1(); SCHED_FENCE(); }
#define PUMP() if (h == 0) PUMP1()
#define WSTEP() { \
      const uint32_t s4 = (ub - bar_full - 256) >> 1; \
      const uint32_t da = dA0 + (((uint32_t)(WO_ASLOT(par) >> s4) & 15) << 10), db = dB0 + (((uint32_t)(WO_BSLOT >> s4) & 15) << 10); \
      mbar_wait(ub, par); \
      wgmma_fence(); \
      wgmma4_n128<1>(S1, da, db); \
      wgmma_commit(); PROFS(); \
      wgmma_wait<1>(); \
      if (s4) REL(ub + 376); \
      ub += 8; }
#define PUMPS(n) { _Pragma("unroll 1") for (int i_ = 0; i_ < (n); i_++) PUMP1(); }
#define SITE(n) { if ((BMASK >> (n)) & 1) PUMP1(); SCHED_FENCE(); }
#define LNSTEP(ACC, hh) { wgmma_fence(); wgmma_n192<1, 0>(ACC, make_desc(sbase + OFF_LNA + wg * 1024, 0, 128) ^ (1ull << 62), make_desc(sbase + OFF_LNB + (hh) * 4096, 0, 128) ^ (1ull << 62)); }
#define DRAIN_A(ACC, PMP) { \
      LANE_CONSTS(); \
      STAGE64(ACC, 64, pV, 1, 1); \
      PMP; \
      STAGE64(ACC, 32, pK, 0, 1); \
      STG_ARRIVE(); \
      _Pragma("unroll") for (int i_ = 0; i_ < 16; i_++) qa[i_] = pack_bf16(ACC[2 * i_], ACC[2 * i_ + 1]); \
      PINU(qa, 16); }
#define DRAIN_B(ACC) { \
      LANE_CONSTS(); \
      STAGE64(ACC, 64, pV, 1, 0); \
      _Pragma("unroll") for (int i_ = 0; i_ < 64; i_++) st[i_] = ACC[i_]; \
      PIN(st, 64); }
#define WARP_STORE(tm, tile, col, row) { fence_proxy_async_smem(); __syncwarp(); \
      if (elect_one()) { tma_store_2d(tm, (tile) + r0 * 128, col, (row) + r0); asm volatile("cp.async.bulk.commit_group;" ::: "memory"); } __syncwarp(); }
#define PUBLISH_O() { if (h) WARP_STORE(&tm_os, pO, jj * 128 + 64, mm * 128) else { fence_proxy_async_smem(); bar_arrive<BAR_O, 288>(); } }
#define X_OUT(pc, on) { \
      PMASKS(on, X_BIT(l)); \
      _Pragma("unroll") for (int j = (pc) * 4; j < (pc) * 4 + 4; j++) \
        stsm_x4(pK + (pc) * SLOT + srowoff + ((((uint32_t)(j & 3) << 5) + lhi) ^ lsw), \
                PBIT0(pack_bf16(S1[j * 8 + 0], S1[j * 8 + 1])), PBIT0(pack_bf16(S1[j * 8 + 2], S1[j * 8 + 3])), \
                PBIT1(pack_bf16(S1[j * 8 + 4], S1[j * 8 + 5])), PBIT1(pack_bf16(S1[j * 8 + 6], S1[j * 8 + 7]))); }
#define REST_P1(SKEW) { \
      mbar_wait(bar_stat2, par); \
      LNSTEP(S1, 1); \
      _Pragma("unroll 1") while (ub < bar_full + 256) { \
        if (ub == bar_full + 256 - 8 * (SKEW) && wg == 0) bar_sync<BAR_SKEW, 256>(); \
        QSTEP(S1, RA_CUR, 1, {}); \
        if (ub == bar_full + 248 && wg == 1) bar_arrive<BAR_SKEW, 256>(); \
        QREL(); \
      } \
      hbase += 256; \
      mbar_wait(bar_done + (31 - (SKEW)) * 8, par);        \
      wgmma_wait<0>(); \
      ACC_FENCE(S1, 96); \
      REL(bar_done + 31 * 8); \
      PROF(13); }
#define FOLD(tile, rd) { \
          LANE_CONSTS(); \
          float d[32]; \
          ACC_DEF(d, 32); \
          mbar_wait(bar_phi + (rd) * 8, 0); \
          wgmma_fence(); \
          _Pragma("unroll") for (int i = 0; i < 2; i++) { \
            const uint64_t da = make_desc((tile) + wg * 8192 + i * 64, 16, 1024); \
            const uint64_t db = make_desc(sbase + OFF_PHI + wg * 4096 + i * 2048, 16, 512) ^ (3ull << 62); \
            wgmma_n32<0>(d + i * 16, da, db); wgmma_n32<1>(d + i * 16, da + 2, db + 64); \
          } \
          wgmma_commit(); \
          PUMP0(); \
          ACC_FENCE(d, 32); \
          bar_wg(wg); \
          _Pragma("unroll") for (int i = 0; i < 4; i++) { \
            const float* x = d + (i & 1) * 8 + (i >> 1) * 2; \
            if (rd) sts128((tile) + wg * 8192 + ((warp & 3) * 16 + (i >> 1) * 8 + g) * 128 + (((2 * t + (i & 1)) ^ g) << 4), \
                           pack_bf16(x[0], x[1]), pack_bf16(x[4], x[5]), pack_bf16(x[16], x[17]), pack_bf16(x[20], x[21])); \
            else stsm_x4((tile) + srowoff + ((((uint32_t)i << 5) + lhi) ^ lsw), pack_bf16(d[i * 8], d[i * 8 + 1]), pack_bf16(d[i * 8 + 2], d[i * 8 + 3]), \
                         pack_bf16(d[i * 8 + 4], d[i * 8 + 5]), pack_bf16(d[i * 8 + 6], d[i * 8 + 7])); \
          } \
          fence_proxy_async_smem(); \
          bar_arrive<BAR_WF + 3 * (rd), 288>(); }
#define LOAD_X0(base) \
      _Pragma("unroll") for (int j = 0; j < 8; j++) { \
        uint32_t x0, x1, x2, x3; \
        ldsm_x4((base) + (j >> 2) * SLOT + srowoff + ((((uint32_t)(j & 3) << 5) + lhi) ^ lsw), x0, x1, x2, x3); \
        S1[j * 8 + 0] = bf_lo(x0); S1[j * 8 + 1] = bf_hi(x0); S1[j * 8 + 2] = bf_lo(x1); S1[j * 8 + 3] = bf_hi(x1); \
        S1[j * 8 + 4] = bf_lo(x2); S1[j * 8 + 5] = bf_hi(x2); S1[j * 8 + 6] = bf_lo(x3); S1[j * 8 + 7] = bf_hi(x3); \
      }
#define LOAD_X() { \
      wgmma_wait<0>(); \
      mbar_wait(bar_xr, par); \
      LOAD_X0(sbase + OFF_RA); \
      ACC_FENCE(S1, 64); \
      __syncwarp(); if (elect_one()) mbar_arrive_local(bar_lx); }

    float S1[96];
#pragma unroll
    for (int i = 0; i < 64; i++) S1[i] = 0.f;
#pragma unroll 1
    for (int l = 0; l < NLAYERS; l++) {
      const uint32_t par = l & 1;
      bar_wg(wg);
      PROF(0);
      uint32_t ub = bar_full;
      const bool hsend = (warp == 7) && (mm < 15);
      const uint32_t hbit = (NLAYERS > 2) ? (l == 0) : (ep1 & 1);
      float S0[96];
      {
        LANE_CONSTS();
        ACC_DEF(S0, 96);
        QSTEP(S0, dA0 + (OFF_S >> 4), 0, {});
        ub += 8;
        PROF(1);
        if (l == 0) { mbar_wait(ub, 0); LOAD_X0(pK); }
        else { X_OUT(1, false); fence_proxy_async_smem(); }
        SCHED_FENCE();
        {
          float a0 = S1[0], a1 = S1[2], b0 = S1[1], b1 = S1[3];
#pragma unroll
          for (int i = 4; i < 64; i += 4) { a0 += S1[i]; b0 += S1[i + 1]; a1 += S1[i + 2]; b1 += S1[i + 3]; }
          a0 += b0; a1 += b1;
          a0 += __shfl_xor_sync(0xffffffffu, a0, 1); a1 += __shfl_xor_sync(0xffffffffu, a1, 1);
          a0 += __shfl_xor_sync(0xffffffffu, a0, 2); a1 += __shfl_xor_sync(0xffffffffu, a1, 2);
          a0 *= (1.f / 128.f); a1 *= (1.f / 128.f);
          asm volatile("" : "+f"(a0), "+f"(a1));
          bar_wg(wg);
          QSTEP(S0, dA0 + ((OFF_S + SLOT) >> 4), 1, wgmma_wait<0>());
          REL(ub + 376); ub += 8;
          SCHED_FENCE();
          float q0 = 0.f, q1 = 0.f;
          b0 = 0.f; b1 = 0.f;
#pragma unroll
          for (int i = 0; i < 64; i += 4) {
            const float d0 = S1[i] - a0, d1 = S1[i + 1] - a0, d2 = S1[i + 2] - a1, d3 = S1[i + 3] - a1;
            q0 = fmaf(d0, d0, q0); b0 = fmaf(d1, d1, b0); q1 = fmaf(d2, d2, q1); b1 = fmaf(d3, d3, b1);
          }
          q0 += b0; q1 += b1;
          q0 += __shfl_xor_sync(0xffffffffu, q0, 1); q1 += __shfl_xor_sync(0xffffffffu, q1, 1);
          q0 += __shfl_xor_sync(0xffffffffu, q0, 2); q1 += __shfl_xor_sync(0xffffffffu, q1, 2);
          if (t < 2) st_b64(g_stats + (size_t)(mm * 128 + r0 + g + t * 8) * 8 + jj, __float_as_uint(t ? a1 : a0), (__float_as_uint(t ? q1 : q0) & ~3u) | STAT_TAG(l));
        }
        if (l) { asm volatile("cp.async.bulk.wait_group 0;" ::: "memory"); bar_arrive<BAR_O + 3, 288>(); }
        ACC_DEF(S1, 96);
        QSTEP(S1, dA0 + (OFF_S >> 4), 0, {});
        QREL();
        QSTEP(S1, dA0 + ((OFF_S + SLOT) >> 4), 1, {});
        QREL();
#pragma unroll 1
        for (int i = 0; i < 14; i++) {
          QSTEP(S0, RA_CUR, 1, {});
          if (i == 0) PROF(2);
          QREL();
        }
      }
      LANE_CONSTS();
      uint4* hbase = g_halo + (size_t)(mm * 8 + jj) * 512;
      mbar_wait(bar_stat, par);
      LNSTEP(S0, 0);
      wgmma_commit();
      const float rs0 = lds32f(sbase + OFF_ST + (r0 + g) * 4), rs1 = lds32f(sbase + OFF_ST + (r0 + g + 8) * 4);
      PUMP0();
      ACC_FENCE(S0, 96);
      PROF(3);
      if (!par) {
        constexpr uint32_t par = 0;
        uint32_t qa[16];
        DRAIN_A(S0, PUMP0());
#pragma unroll 1
        for (int h = 0; h < 2; h++) {
          const uint32_t pO = sbase + (h ? 3 : 12) * SLOT;
          PROF(4 + h * 12);
          const bool fold = (l == 0 && h == 0 && NLAYERS > 1);
          if (fold) FOLD(pO, 0) else if (h == 0) PUMPS(HPUMP1);
          LANE_CONSTS();
          uint4 hv[8];
#pragma unroll
          for (int i = 0; i < 8; i++) hv[i] = make_uint4(hbit, 0, 0, 0);
          const bool hrec = (warp == 0 && mm > 0);
          if (hrec) {
#pragma unroll
            for (int i = 0; i < 8; i++) hv[i] = ld_b128(hbase + lane - 8 * 512 + i * 32);
          }
          if (h) LOAD_X() else PUMPS(HPUMP2);
          const uint32_t halo = sbase + OFF_HALO;
          STG_WAIT();
          if (warp == 0) {
#pragma unroll 1
            for (int it = 0; it < (1 << 16); it++) {
              uint32_t bad = 0;
#pragma unroll
              for (int i = 0; i < 8; i++) bad |= hv[i].x ^ hbit;
              if (__all_sync(0xffffffffu, (bad & 1) == 0)) break;
#pragma unroll
              for (int i = 0; i < 8; i++) hv[i] = ld_b128(hbase + lane - 8 * 512 + i * 32);
            }
#pragma unroll
            for (int i = 0; i < 8; i++)
              stsm_x4(i < 4 ? halo + srowoff + ((((uint32_t)i << 5) + lhi) ^ lsw)
                            : halo + (srowoff >> 1) + (i >> 1) * 1024 + ((((uint32_t)(i & 1) << 5) + lhi) ^ lsw2), hv[i].x, hv[i].y, hv[i].z, hv[i].w);
            __syncwarp();
          }
          PROF(5 + h * 12);
          const uint32_t kb1 = pK + r0 * 128, vb1 = pV + r0 * 64;
          const uint32_t kb0 = r0 ? kb1 - 2048 : halo, vb0 = r0 ? vb1 - 1024 : halo + 2048;
          const uint32_t vhs = r0 ? 8192 : 1024;
          float s[2][4][4];
          {
            uint32_t kf[2][4][4];
#pragma unroll
            for (int i = 0; i < 8; i++) {
              const int hh = i >> 2, jb = i & 3;
              ldsm_x4(((jb < 2) ? kb0 : kb1) + ((jb & 1) * 8 + (lane & 7)) * 128 + ((hh * 64 + ((lane >> 3) << 4)) ^ lsw), kf[hh][jb][0], kf[hh][jb][1], kf[hh][jb][2], kf[hh][jb][3]);
              s[hh][jb][0] = s[hh][jb][1] = s[hh][jb][2] = s[hh][jb][3] = 0.f;
            }
#pragma unroll
            for (int ks = 0; ks < 2; ks++)
#pragma unroll
              for (int i = 0; i < 8; i++) {
                const int hh = i >> 2, jb = i & 3;
                mma_bf16(s[hh][jb], qa[hh * 8 + ks * 4], qa[hh * 8 + ks * 4 + 1], qa[hh * 8 + ks * 4 + 2], qa[hh * 8 + ks * 4 + 3], kf[hh][jb][ks * 2], kf[hh][jb][ks * 2 + 1]);
              }
          }
          PUMP();
          if (fold) bar_arrive<BAR_WF + 2, 288>();
          PROF(6 + h * 12);
          const bool e = g & 1, hb = (2 * t + (g & 1)) <= g;
          uint32_t vf[2][2][2][4];
#pragma unroll
          for (int i = 0; i < 8; i++) {
            const int hh = i >> 2, ks = (i >> 1) & 1, dp = i & 1;
            ldsm_x4_t((ks ? vb1 + hh * 8192 : vb0 + hh * vhs) + (lane & 15) * 64 + ((dp * 32 + lhi) ^ lsw2), vf[hh][ks][dp][0], vf[hh][ks][dp][1], vf[hh][ks][dp][2], vf[hh][ks][dp][3]);
          }
          float va[2][2], vb[2][2], mx[2][2];
#pragma unroll
          for (int hh = 0; hh < 2; hh++) {
            va[hh][0] = e ? s[hh][1][1] : s[hh][1][0];
            vb[hh][0] = hb ? (e ? s[hh][2][1] : s[hh][2][0]) : (e ? s[hh][0][1] : s[hh][0][0]);
            va[hh][1] = e ? s[hh][2][3] : s[hh][2][2];
            vb[hh][1] = hb ? (e ? s[hh][3][3] : s[hh][3][2]) : (e ? s[hh][1][3] : s[hh][1][2]);
          }
          if (warp == 0 && mm == 0) {
#pragma unroll
            for (int hh = 0; hh < 2; hh++) { va[hh][0] = -INFINITY; if (!hb) { vb[hh][0] = -INFINITY; vb[hh][1] = -INFINITY; } }
          }
#pragma unroll
          for (int i = 0; i < 4; i++) mx[i >> 1][i & 1] = fmaxf(va[i >> 1][i & 1], vb[i >> 1][i & 1]);
#pragma unroll
          for (int o = 1; o <= 2; o <<= 1)
#pragma unroll
            for (int i = 0; i < 4; i++) mx[i >> 1][i & 1] = fmaxf(mx[i >> 1][i & 1], __shfl_xor_sync(0xffffffffu, mx[i >> 1][i & 1], o));
          const float sc0 = rs0 * (0.17677669529663687f * LOG2E), sc1 = rs1 * (0.17677669529663687f * LOG2E);
#pragma unroll
          for (int i = 0; i < 4; i++) {
            const float sc = (i & 1) ? sc1 : sc0, m = mx[i >> 1][i & 1];
            va[i >> 1][i & 1] = ex2((va[i >> 1][i & 1] - m) * sc); vb[i >> 1][i & 1] = ex2((vb[i >> 1][i & 1] - m) * sc);
            mx[i >> 1][i & 1] = va[i >> 1][i & 1] + vb[i >> 1][i & 1];
          }
          if (h == 0 && ASITE) { PIN(&va[0][0], 4); PIN(&vb[0][0], 4); PIN(&mx[0][0], 4); PUMP1(); }
#pragma unroll
          for (int o = 1; o <= 2; o <<= 1)
#pragma unroll
            for (int i = 0; i < 4; i++) mx[i >> 1][i & 1] += __shfl_xor_sync(0xffffffffu, mx[i >> 1][i & 1], o);
          const uint32_t selA = e ? 0x1044 : 0x4410, selB = e ? 0x3244 : 0x4432, selL = hb ? 0x4444 : selB, selH = hb ? selB : 0x4444;
          float o[2][4][4];
          uint32_t pa[2][6];
#pragma unroll
          for (int hh = 0; hh < 2; hh++) {
            const float i0 = rcp_fast(mx[hh][0]), i1 = rcp_fast(mx[hh][1]);
            const uint32_t w0 = pack_bf16(va[hh][0] * i0, vb[hh][0] * i0), w1 = pack_bf16(va[hh][1] * i1, vb[hh][1] * i1);
            pa[hh][0] = __byte_perm(w0, 0, selL); pa[hh][1] = __byte_perm(w0, 0, selA); pa[hh][2] = __byte_perm(w1, 0, selL);
            pa[hh][3] = __byte_perm(w0, 0, selH); pa[hh][4] = __byte_perm(w1, 0, selA); pa[hh][5] = __byte_perm(w1, 0, selH);
#pragma unroll
            for (int dj = 0; dj < 4; dj++) { o[hh][dj][0] = o[hh][dj][1] = o[hh][dj][2] = o[hh][dj][3] = 0.f; }
          }
          PROF(7 + h * 12);
#pragma unroll
          for (int i = 0; i < 8; i++) mma_bf16(o[i >> 2][i & 3], pa[i >> 2][0], 0u, pa[i >> 2][1], pa[i >> 2][2], vf[i >> 2][0][(i >> 1) & 1][(i & 1) * 2], vf[i >> 2][0][(i >> 1) & 1][(i & 1) * 2 + 1]);
#pragma unroll
          for (int i = 0; i < 8; i++) mma_bf16(o[i >> 2][i & 3], pa[i >> 2][3], pa[i >> 2][4], 0u, pa[i >> 2][5], vf[i >> 2][1][(i >> 1) & 1][(i & 1) * 2], vf[i >> 2][1][(i >> 1) & 1][(i & 1) * 2 + 1]);
          if (h == 0) PUMP1() else mbar_wait(bar_done + 30 * 8, par);
          if (fold) mbar_wait(bar_phi, 1);
#pragma unroll
          for (int i = 0; i < 4; i++) {
            const int hh = i >> 1, dp = i & 1;
            PMASKS(h, O_BIT(l));
            stsm_x4(pO + srowoff + ((hh * 64 + dp * 32 + lhi) ^ lsw), PBIT0(pack_bf16(o[hh][dp * 2][0], o[hh][dp * 2][1])), PBIT0(pack_bf16(o[hh][dp * 2][2], o[hh][dp * 2][3])),
                    PBIT1(pack_bf16(o[hh][dp * 2 + 1][0], o[hh][dp * 2 + 1][1])), PBIT1(pack_bf16(o[hh][dp * 2 + 1][2], o[hh][dp * 2 + 1][3])));
          }
          PUBLISH_O();
          PROF(11 + h * 12);
          if (h) break;
          if (fold) { PUMPS(FPUMP); FOLD(pK, 1); }
          REST_P1(ASKEW);
          if (fold) mbar_wait(bar_phi + 8, 1);
          DRAIN_A(S1, {});
        }
      } else {
        constexpr uint32_t par = 1;
        float st[64];
        DRAIN_B(S0);
        if (warp < 2) sts128(sbase + OFF_ONES + warp * 512 + lane * 16, 0x3F803F80u, 0x3F803F80u, 0x3F803F80u, 0x3F803F80u);
        const float c0 = rs0 * LOG2E, c1 = rs1 * LOG2E;
#define KV_PART(hp, ...) { \
          float kv[20]; \
          ACC_DEF(kv, 20); \
          const uint64_t dp = make_desc(wg ? pK : sbase + 12 * SLOT, 16, 1024); \
          const uint64_t dv = (make_desc(pV + wg * 8192, OFF_ONES - OFF_S - SLOT - wg * 8192, 512) ^ (3ull << 62)); \
          constexpr uint64_t DVS = 64ull - (64ull << 16); \
          fence_proxy_async_smem(); \
          STG_ARRIVE(); \
          STG_WAIT(); \
          wgmma_fence(); \
          _Pragma("unroll") for (int ks = 0; ks < 8; ks++) { if (ks == 0) wgmma_n40<0, 1>(kv, dp, dv); else wgmma_n40<1, 1>(kv, dp + ks * 128, dv + ks * DVS); } \
          wgmma_commit(); \
          __VA_ARGS__; \
          ACC_FENCE(kv, 20); \
          float* kvg = g_kv[l >> 1] + (jj * 4 + (hp) * 2 + wg) * KVH + ((warp & 3) * 32 + lane) * 4; \
          _Pragma("unroll") for (int i = 0; i < 4; i++) red_v4(kvg + i * 512, kv[i * 4], kv[i * 4 + 1], kv[i * 4 + 2], kv[i * 4 + 3]); \
          if (t == 0) red_v4(kvg + 2048, kv[16], kv[17], kv[18], kv[19]); \
          bar_arrive<BAR_KV + (hp), 288>(); \
          STG_ARRIVE(); }
#pragma unroll 1
        for (int h = 0; h < 2; h++) {
          PROF(4 + h * 2);
          SITE(0);
          LANE_CONSTS();
          const uint32_t dsw = (uint32_t)(g ^ (2 * t)) << 4, dst = ((t & 2) ? pK : sbase + 12 * SLOT) + (r0 + g) * 128;
          float e[16], f[16];
          float mn0 = rmin16(st);
          asm volatile("" : "+f"(mn0)); SCHED_FENCE();
          float sa = exps16(e, st, -c0, mn0 * c0), mx0 = rmax16(st);
          asm volatile("" : "+f"(sa), "+f"(mx0)); PIN(e, 16); SITE(1);
          if (h) STG_WAIT();
          store16(e, sa, dst, dsw, 4);
          float sb = exps16(f, st, c0, -mx0 * c0), mn1 = rmin16(st + 2);
          asm volatile("" : "+f"(sb), "+f"(mn1)); PIN(f, 16); SITE(2);
          store16(f, sb, dst, dsw, 0);
          float sc = exps16(e, st + 2, -c1, mn1 * c1), mx1 = rmax16(st + 2);
          asm volatile("" : "+f"(sc), "+f"(mx1)); PIN(e, 16); SITE(3);
          store16(e, sc, dst + 1024, dsw, 4);
          float sd = exps16(f, st + 2, c1, -mx1 * c1);
          asm volatile("" : "+f"(sd)); PIN(f, 16); SITE(4);
          store16(f, sd, dst + 1024, dsw, 0);
          PROF(5 + h * 2);
          if (h) break;
          KV_PART(0, PUMP0());
#pragma unroll
          for (int i = 0; i < 32; i++) st[i] = st[32 + i];
        }
        REST_P1(1);
        float mq[16];
        {
          LANE_CONSTS();
          DRAIN_B(S1);
          PROF(16);
          KV_PART(1, { SCHED_FENCE(); extrema(mq, st, c0, c1); extrema(mq + 8, st + 32, c0, c1); PIN(mq, 16); wgmma_wait<0>(); });
          STG_WAIT();
          PROF(17);
        }
#pragma unroll 1
        for (int h = 0; h < 2; h++) {
          const uint32_t pO = sbase + (h ? 3 : 12) * SLOT, pT = h ? pV : pK;
          LANE_CONSTS();
          const float4* kvg = reinterpret_cast<const float4*>(g_kv[l >> 1] + (jj * 4 + h * 2 + wg) * KVH) + (warp & 3) * 32 + lane;
          float4 v[5];
          uint32_t fq[32];
          if (KVLATE) { expp16(fq, st, -c0, mq[0], -c1, mq[1]); expp16(fq + 8, st, c0, mq[2], c1, mq[3]); PINU(fq, 16); }
          mbar_wait(bar_kvf + h * 8, l >> 1);
          PROF(25 + h);
#pragma unroll
          for (int i = 0; i < 4; i++) v[i] = __ldcg(kvg + i * 128);
          v[4] = __ldcg(kvg + 512 - t);
          if (!KVLATE) { expp16(fq, st, -c0, mq[0], -c1, mq[1]); expp16(fq + 8, st, c0, mq[2], c1, mq[3]); PINU(fq, 16); }
          else { expp16(fq + 16, st + 16, -c0, mq[4], -c1, mq[5]); expp16(fq + 24, st + 16, c0, mq[6], c1, mq[7]); PINU(fq + 16, 16); }
          SCHED_FENCE();
          PROF(18 + h * 14);
          {
            const uint32_t e = lane & 7, jt = ((lane >> 1) & 4) + (e >> 1);
            const uint32_t row = ((((warp >> 1) ^ wg) & 1) << 5) + ((jt & 1) << 4) + ((warp & 1) << 3) + (jt & 6) + (e & 1);
            const uint32_t kd = pT + wg * 8192 + row * 128, ksw = (row & 7) << 4;
#pragma unroll
            for (int i = 0; i < 2; i++) {
              const float4 a = v[i * 2], b = v[i * 2 + 1];
              stsm_x4(kd + ((i * 32 + lhi) ^ ksw), pack_bf16(a.x, a.y), pack_bf16(a.z, a.w), pack_bf16(b.x, b.y), pack_bf16(b.z, b.w));
            }
            stsm_x4(kd + ((64u + lhi) ^ ksw), pack_bf16(v[4].x, 1.f), pack_bf16(v[4].z, 1.f), 0u, 0u);
          }
          fence_proxy_async_smem();
          STG_ARRIVE();
          if (!KVLATE) { expp16(fq + 16, st + 16, -c0, mq[4], -c1, mq[5]); PINU(fq + 16, 8); }
          float o[4][20];
          STG_WAIT();
          PROF(19 + h * 14);
#pragma unroll
          for (int hh = 0; hh < 2; hh++) {
            const uint64_t db = make_desc(pT + hh * 8192, 16, 1024);
            if (hh && !KVLATE) { SCHED_FENCE(); expp16(fq + 24, st + 16, c0, mq[6], c1, mq[7]); PINU(fq + 24, 8); }
            if (hh) { wgmma_wait<0>(); ACC_FENCE(o[0], 20); ACC_FENCE(o[1], 20); }
            ACC_DEF(o[hh * 2], 20); ACC_DEF(o[hh * 2 + 1], 20);
            wgmma_fence();
#pragma unroll
            for (int sg = 0; sg < 2; sg++) {
              wgmma_n40_rs<0>(o[hh * 2 + sg], fq + hh * 16 + sg * 8, db + (sg ^ 1) * 256);
              wgmma_n40_rs<1>(o[hh * 2 + sg], fq + hh * 16 + sg * 8 + 4, db + (sg ^ 1) * 256 + 128);
            }
            wgmma_commit();
          }
          PMASKS(h, O_BIT(l));
#pragma unroll
          for (int hh = 0; hh < 2; hh++) {
            if (hh) { wgmma_wait<0>(); ACC_FENCE(o[2], 20); ACC_FENCE(o[3], 20); } else SCHED_FENCE();
            const float* x = o[hh * 2];
            const float* y = o[hh * 2 + 1];
            const float rx0 = rcp_fast(x[17]), ry0 = rcp_fast(y[17]), rx1 = rcp_fast(x[19]), ry1 = rcp_fast(y[19]);
            const float i0 = rcp_fast(fmaf(x[16], rx0, y[16] * ry0) + 1e-6f), i1 = rcp_fast(fmaf(x[18], rx1, y[18] * ry1) + 1e-6f);
            const float ax0 = rx0 * i0, ay0 = ry0 * i0, ax1 = rx1 * i1, ay1 = ry1 * i1;
#pragma unroll
            for (int dp = 0; dp < 2; dp++)
              stsm_x4(pO + srowoff + ((hh * 64 + dp * 32 + lhi) ^ lsw),
                      PBIT0(pack_bf16(fmaf(x[dp * 8], ax0, y[dp * 8] * ay0), fmaf(x[dp * 8 + 1], ax0, y[dp * 8 + 1] * ay0))),
                      PBIT0(pack_bf16(fmaf(x[dp * 8 + 2], ax1, y[dp * 8 + 2] * ay1), fmaf(x[dp * 8 + 3], ax1, y[dp * 8 + 3] * ay1))),
                      PBIT1(pack_bf16(fmaf(x[dp * 8 + 4], ax0, y[dp * 8 + 4] * ay0), fmaf(x[dp * 8 + 5], ax0, y[dp * 8 + 5] * ay0))),
                      PBIT1(pack_bf16(fmaf(x[dp * 8 + 6], ax1, y[dp * 8 + 6] * ay1), fmaf(x[dp * 8 + 7], ax1, y[dp * 8 + 7] * ay1))));
          }
          PUBLISH_O();
          PROF(20 + h * 14);
          if (h) break;
#pragma unroll
          for (int i = 0; i < 32; i++) st[i] = st[32 + i];
#pragma unroll
          for (int i = 0; i < 8; i++) mq[i] = mq[8 + i];
        }
        LANE_CONSTS();
        LOAD_X();
      }
      __syncwarp();
      if (elect_one()) mbar_arrive_local(bar_epi);
      bar_wg(wg);
#pragma unroll 1
      while (ub < bar_full + 384) {
        WSTEP();
        if (ub == bar_full + 8 * 41) { asm volatile("cp.async.bulk.wait_group.read 0;" ::: "memory"); PROF(35); }
        if (ub == bar_full + 8 * 42) PROF(36);
      }
      wgmma_wait<0>();
      ACC_FENCE(S1, 64);
      REL(bar_done + 47 * 8);
      PROF(37);
      {
        LANE_CONSTS();
        X_OUT(0, l < NLAYERS - 1);
        WARP_STORE(l < NLAYERS - 1 ? &tm_os : &tm_xo, pK, jj * 128, mm * 128 + (l < NLAYERS - 1 ? S_LEN : 0));
        if (l == NLAYERS - 1) {
          X_OUT(1, false);
          WARP_STORE(&tm_xo, pV, jj * 128 + 64, mm * 128);
          asm volatile("cp.async.bulk.wait_group 0;" ::: "memory");
        }
      }
#pragma unroll
      for (int i = 32; i < 64; i++) { uint32_t c; asm volatile("mov.b32 %0, %1;" : "=r"(c) : "f"(S1[i])); S1[i] = __uint_as_float(c); }
      PROF(38);
    }
    const int tid = threadIdx.x;
    if (tid == 0) {
      unsigned old = atomicAdd(&g_flags.done.v, 1);
      if (old == ep1 * NMAIN - 1) {
        asm volatile("st.relaxed.gpu.global.u32 [%0], %1;" :: "l"(&g_flags.epoch.v), "r"(ep1) : "memory");
      }
    }
    __syncwarp();
    cluster_sync();
  }
}

typedef CUresult (*PFN_encode)(CUtensorMap*, CUtensorMapDataType, cuuint32_t, void*, const cuuint64_t*, const cuuint64_t*,
                               const cuuint32_t*, const cuuint32_t*, CUtensorMapInterleave, CUtensorMapSwizzle,
                               CUtensorMapL2promotion, CUtensorMapFloatOOBfill);

CUtensorMap make_map(PFN_encode enc, const void* ptr, uint64_t inner, uint64_t outer, uint32_t box_inner, uint32_t box_outer,
                     CUtensorMapSwizzle swz = CU_TENSOR_MAP_SWIZZLE_128B) {
  CUtensorMap m;
  cuuint64_t dims[2] = {inner, outer};
  cuuint64_t strides[1] = {inner * 2};
  cuuint32_t box[2] = {box_inner, box_outer};
  cuuint32_t es[2] = {1, 1};
  enc(&m, CU_TENSOR_MAP_DATA_TYPE_BFLOAT16, 2, const_cast<void*>(ptr), dims, strides, box, es, CU_TENSOR_MAP_INTERLEAVE_NONE,
      swz, CU_TENSOR_MAP_L2_PROMOTION_L2_256B, CU_TENSOR_MAP_FLOAT_OOB_FILL_NONE);
  return m;
}

}

extern "C" void kernel_launch(void* const* d_in, const int* in_sizes, int n_in, void* d_out, int out_size) {
  (void)in_sizes; (void)n_in; (void)out_size;
  static PFN_encode enc = nullptr;
  if (!enc) {
    void* fn = nullptr;
    cudaDriverEntryPointQueryResult qr;
    cudaGetDriverEntryPoint("cuTensorMapEncodeTiled", &fn, cudaEnableDefault, &qr);
    enc = (PFN_encode)fn;
    cudaFuncSetAttribute(mega_kernel, cudaFuncAttributeMaxDynamicSharedMemorySize, SMEM_BYTES);
  }
  Params prm;
  prm.x0 = (const __nv_bfloat16*)d_in[0];
  prm.wA_qkv = (const __nv_bfloat16*)d_in[1];
  prm.wA_o = (const __nv_bfloat16*)d_in[2];
  prm.wB_qkv = (const __nv_bfloat16*)d_in[4];
  prm.wB_phi = (const __nv_bfloat16*)d_in[5];
  prm.wB_o = (const __nv_bfloat16*)d_in[6];
  prm.out = (__nv_bfloat16*)d_out;
  void *obuf = nullptr, *wf = nullptr;
  cudaGetSymbolAddress(&obuf, g_obuf);
  cudaGetSymbolAddress(&wf, g_wfold);
  CUtensorMap tm_x0 = make_map(enc, d_in[0], D_MODEL, S_LEN, 64, 128);
  CUtensorMap tm_xo = make_map(enc, d_out, D_MODEL, S_LEN, 64, 16);
  CUtensorMap tm_os = make_map(enc, obuf, D_MODEL, 2 * S_LEN, 64, 16);
  CUtensorMap tm_o = make_map(enc, obuf, D_MODEL, 2 * S_LEN, 64, 128);
  CUtensorMap tm_wf = make_map(enc, wf, 2048, D_MODEL, 64, 32);
  CUtensorMap tm_wqA = make_map(enc, d_in[1], 3 * D_MODEL, D_MODEL, 64, 32);
  CUtensorMap tm_wqB = make_map(enc, prm.wB_qkv, 3 * D_MODEL, D_MODEL, 64, 32);
  CUtensorMap tm_woA = make_map(enc, prm.wA_o, D_MODEL, D_MODEL, 64, 64);
  CUtensorMap tm_woB = make_map(enc, prm.wB_o, D_MODEL, D_MODEL, 64, 64);
  CUtensorMap tm_phi = make_map(enc, prm.wB_phi, 32, 1024, 32, 128, CU_TENSOR_MAP_SWIZZLE_64B);
  mega_kernel<<<NMAIN + NAUX, 384, SMEM_BYTES>>>(tm_x0, tm_xo, tm_os, tm_o, tm_wf, tm_wqA, tm_wqB, tm_woA, tm_woB, tm_phi, prm);
}
```

```cpp
#include <cuda_runtime.h>
#include <cuda.h>
#include <cuda_bf16.h>
#include <stdint.h>

#define NLAYERS 4

#define STAG1 300
#define HPUMP1 2
#define HPUMP2 2
#define ASKEW 2
#define FPUMP 2
#define PFGAP 100
#define POLLW 4
#define POLL0 0
#define POLLGAP 120
#define OW 1
#define FILL 40
#define BMASK 0x1F
#define ASITE 1
namespace {

constexpr int S_LEN = 2048, D_MODEL = 1024;
constexpr int NAUX = 4, NMAIN = 128;
constexpr int SLOT = 16384;
constexpr int QST = 24576;
constexpr int OFF_RA = 6 * SLOT, OFF_S = 10 * SLOT;
constexpr int OFF_HALO = 13 * SLOT, OFF_LNB = OFF_HALO  , OFF_ONES = OFF_HALO + 3072;
constexpr int OFF_ST = OFF_HALO + 7168  , OFF_PHI = OFF_HALO + 8192;
constexpr int OFF_BAR = 14 * SLOT;
constexpr int OFF_LNA = OFF_BAR + 1024;
constexpr int SMEM_BYTES = OFF_LNA + 2048;
#define WO_ASLOT(par) ((par) ? 0x9876CAB39876CA98ull : 0x98C76BA398C7698Cull)
constexpr unsigned long long WO_BSLOT = 0x5432105421054210ull;
__device__ __forceinline__ int kslice(int j, int i) { return i < 2 ? 2 * j + i : (i < 9 ? 2 * ((j + i - 1) & 7) : 2 * ((j + i) & 7) + 1); }
__device__ __forceinline__ int wslice(int j, int s) { return 2 * ((j + s) & 7) + (s >> 3); }
constexpr int KVH = 5 * 128 * 4;

struct __align__(128) Flag { unsigned v; unsigned pad[31]; };
struct Flags {
  Flag xready[4][16];
  Flag kvready[4][8][16];
  Flag wfready[8];
  Flag done;
  Flag epoch;
};

__device__ Flags g_flags;
__device__ __nv_bfloat16 g_obuf[2 * S_LEN * D_MODEL];
#define O_BIT(l) ((epoch * NLAYERS + (l) + 1) & 1u)
#define X_BIT(l) ((epoch * (NLAYERS - 1) + (l) + 1) & 1u)
__device__ __nv_bfloat16 g_wfold[D_MODEL * 2048];
__device__ uint4 g_halo[16 * 8 * 512];
__device__ float g_kv[2][32 * KVH];
__device__ __align__(128) uint2 g_colsum[2][1536][2];
__device__ __align__(128) uint2 g_stats[S_LEN * 8];
#define STAT_TAG(l) ((ep1 * NLAYERS + (l) + 1) & 3u)

#define RETRY_COUNT()
#define PROFL 1
#define PROFW 0
#define KVFLAG 1
#define PROFT(i) do {} while (0)
#define PROF(i) do {} while (0)

__device__ __forceinline__ uint32_t smem_u32(const void* p) { return (uint32_t)__cvta_generic_to_shared(p); }
__device__ __forceinline__ bool elect_one() {
  uint32_t p;
  asm volatile("{\n.reg .pred p;\nelect.sync _|p, 0xffffffff;\nselp.u32 %0, 1, 0, p;\n}\n" : "=r"(p));
  return p != 0;
}
__device__ __forceinline__ void mbar_init(uint32_t bar, uint32_t cnt) {
  asm volatile("mbarrier.init.shared::cta.b64 [%0], %1;" :: "r"(bar), "r"(cnt));
}
__device__ __forceinline__ void mbar_expect_tx(uint32_t bar, uint32_t bytes) {
  asm volatile("mbarrier.arrive.expect_tx.shared::cta.b64 _, [%0], %1;" :: "r"(bar), "r"(bytes) : "memory");
}
#define mbar_wait(bar, parity) \
  asm volatile("{\n.reg .pred p, q;\nW_%=:\nmbarrier.try_wait.parity.shared::cta.b64 p, [%1], %2;\nadd.s32 %0, %0, -1;\n" \
               "setp.gt.and.s32 q, %0, 0, !p;\n@q bra.uni W_%=;\n}\n" : "+r"(budget) : "r"((uint32_t)(bar)), "r"((uint32_t)(parity)) : "memory")
#define mbar_wait_sl(bar, parity) \
  asm volatile("{\n.reg .pred p, q;\nW_%=:\nmbarrier.try_wait.parity.shared::cta.b64 p, [%1], %2, 20000;\nadd.s32 %0, %0, -64;\n" \
               "setp.gt.and.s32 q, %0, 0, !p;\n@q bra.uni W_%=;\n}\n" : "+r"(budget) : "r"((uint32_t)(bar)), "r"((uint32_t)(parity)) : "memory")
__device__ __forceinline__ void mbar_arrive_local(uint32_t bar) {
  asm volatile("mbarrier.arrive.shared::cta.b64 _, [%0];" :: "r"(bar) : "memory");
}
__device__ __forceinline__ void tma_load_2d(uint32_t dst, const CUtensorMap* tm, uint32_t bar, int c0, int c1) {
  asm volatile("cp.async.bulk.tensor.2d.shared::cluster.global.mbarrier::complete_tx::bytes [%0], [%1, {%3, %4}], [%2];"
               :: "r"(dst), "l"(tm), "r"(bar), "r"(c0), "r"(c1) : "memory");
}
__device__ __forceinline__ void tma_load_2d_mc(uint32_t dst, const CUtensorMap* tm, uint32_t bar, int c0, int c1) {
  asm volatile("cp.async.bulk.tensor.2d.shared::cluster.global.mbarrier::complete_tx::bytes.multicast::cluster [%0], [%1, {%3, %4}], [%2], %5;"
               :: "r"(dst), "l"(tm), "r"(bar), "r"(c0), "r"(c1), "h"((uint16_t)3) : "memory");
}
__device__ __forceinline__ void tma_store_2d(const CUtensorMap* tm, uint32_t src, int c0, int c1) {
  asm volatile("cp.async.bulk.tensor.2d.global.shared::cta.bulk_group [%0, {%2, %3}], [%1];"
               :: "l"(tm), "r"(src), "r"(c0), "r"(c1) : "memory");
}
__device__ __forceinline__ void bulk_commit_wait() {
  asm volatile("cp.async.bulk.commit_group;\ncp.async.bulk.wait_group 0;" ::: "memory");
}
__device__ __forceinline__ void prefetch_tmap(const CUtensorMap* tm) {
  asm volatile("prefetch.tensormap [%0];" :: "l"(tm) : "memory");
}
__device__ __forceinline__ void fence_proxy_async_global() { asm volatile("fence.proxy.async.global;" ::: "memory"); }
__device__ __forceinline__ void fence_proxy_async_smem() { asm volatile("fence.proxy.async.shared::cta;" ::: "memory"); }
__device__ __forceinline__ unsigned ld_relaxed(const unsigned* p) {
  unsigned v;
  asm volatile("ld.relaxed.gpu.global.u32 %0, [%1];" : "=r"(v) : "l"(p) : "memory");
  return v;
}
__device__ __forceinline__ void fence_acquire() { asm volatile("fence.acquire.gpu;" ::: "memory"); }
__device__ __forceinline__ void wait_flag(const unsigned* p, unsigned target) {
  int it = 0;
  while ((int)(ld_relaxed(p) - target) < 0 && ++it < (1 << 20)) {}
  fence_acquire();
}
__device__ __forceinline__ void signal_release(unsigned* p) {
  asm volatile("red.release.gpu.global.add.u32 [%0], 1;" :: "l"(p) : "memory");
}
template <int ID, int N> __device__ __forceinline__ void bar_arrive() { asm volatile("bar.arrive %0, %1;" :: "n"(ID), "n"(N) : "memory"); }
template <int ID, int N> __device__ __forceinline__ void bar_sync() { asm volatile("bar.sync %0, %1;" :: "n"(ID), "n"(N) : "memory"); }
__device__ __forceinline__ void bar_wg(int wg) { asm volatile("bar.sync %0, 128;" :: "r"(2 + wg) : "memory"); }
__device__ __forceinline__ void cluster_sync() {
  asm volatile("barrier.cluster.arrive.relaxed.aligned;\nbarrier.cluster.wait.aligned;" ::: "memory");
}
__device__ __forceinline__ void cluster_wait() { asm volatile("barrier.cluster.wait.acquire.aligned;" ::: "memory"); }
enum { BAR_KV = 4  , BAR_O = 7  , BAR_WF = 12  , BAR_SKEW = 13 };

__device__ __forceinline__ void wgmma_fence() { asm volatile("wgmma.fence.sync.aligned;" ::: "memory"); }
__device__ __forceinline__ void wgmma_commit() { asm volatile("wgmma.commit_group.sync.aligned;" ::: "memory"); }
template <int N> __device__ __forceinline__ void wgmma_wait() { asm volatile("wgmma.wait_group.sync.aligned %0;" :: "n"(N) : "memory"); }

template <int scale_d, int tnsp_b = 1> __device__ __forceinline__ void wgmma_n192(float* d, uint64_t descA, uint64_t descB) {
  asm volatile("{\n.reg .pred p;\nsetp.ne.b32 p, %98, 0;\n"
               "wgmma.mma_async.sync.aligned.m64n192k16.f32.bf16.bf16 {%0,%1,%2,%3,%4,%5,%6,%7,%8,%9,%10,%11,%12,%13,%14,%15,%16,%17,%18,%19,%20,%21,%22,%23,%24,%25,%26,%27,%28,%29,%30,%31,%32,%33,%34,%35,%36,%37,%38,%39,%40,%41,%42,%43,%44,%45,%46,%47,%48,%49,%50,%51,%52,%53,%54,%55,%56,%57,%58,%59,%60,%61,%62,%63,%64,%65,%66,%67,%68,%69,%70,%71,%72,%73,%74,%75,%76,%77,%78,%79,%80,%81,%82,%83,%84,%85,%86,%87,%88,%89,%90,%91,%92,%93,%94,%95}, %96, %97, p, 1, 1, 0, %99;\n}\n"
               : "+f"(d[0]), "+f"(d[1]), "+f"(d[2]), "+f"(d[3]), "+f"(d[4]), "+f"(d[5]), "+f"(d[6]), "+f"(d[7]), "+f"(d[8]), "+f"(d[9]), "+f"(d[10]), "+f"(d[11]), "+f"(d[12]), "+f"(d[13]), "+f"(d[14]), "+f"(d[15]), "+f"(d[16]), "+f"(d[17]), "+f"(d[18]), "+f"(d[19]), "+f"(d[20]), "+f"(d[21]), "+f"(d[22]), "+f"(d[23]), "+f"(d[24]), "+f"(d[25]), "+f"(d[26]), "+f"(d[27]), "+f"(d[28]), "+f"(d[29]), "+f"(d[30]), "+f"(d[31]), "+f"(d[32]), "+f"(d[33]), "+f"(d[34]), "+f"(d[35]), "+f"(d[36]), "+f"(d[37]), "+f"(d[38]), "+f"(d[39]), "+f"(d[40]), "+f"(d[41]), "+f"(d[42]), "+f"(d[43]), "+f"(d[44]), "+f"(d[45]), "+f"(d[46]), "+f"(d[47]), "+f"(d[48]), "+f"(d[49]), "+f"(d[50]), "+f"(d[51]), "+f"(d[52]), "+f"(d[53]), "+f"(d[54]), "+f"(d[55]), "+f"(d[56]), "+f"(d[57]), "+f"(d[58]), "+f"(d[59]), "+f"(d[60]), "+f"(d[61]), "+f"(d[62]), "+f"(d[63]), "+f"(d[64]), "+f"(d[65]), "+f"(d[66]), "+f"(d[67]), "+f"(d[68]), "+f"(d[69]), "+f"(d[70]), "+f"(d[71]), "+f"(d[72]), "+f"(d[73]), "+f"(d[74]), "+f"(d[75]), "+f"(d[76]), "+f"(d[77]), "+f"(d[78]), "+f"(d[79]), "+f"(d[80]), "+f"(d[81]), "+f"(d[82]), "+f"(d[83]), "+f"(d[84]), "+f"(d[85]), "+f"(d[86]), "+f"(d[87]), "+f"(d[88]), "+f"(d[89]), "+f"(d[90]), "+f"(d[91]), "+f"(d[92]), "+f"(d[93]), "+f"(d[94]), "+f"(d[95])
               : "l"(descA), "l"(descB), "n"(scale_d), "n"(tnsp_b));
}
template <int scale_d> __device__ __forceinline__ void wgmma4_n192(float* d, uint32_t da, uint32_t db) {
#define R_ "{%0,%1,%2,%3,%4,%5,%6,%7,%8,%9,%10,%11,%12,%13,%14,%15,%16,%17,%18,%19,%20,%21,%22,%23,%24,%25,%26,%27,%28,%29,%30,%31,%32,%33,%34,%35,%36,%37,%38,%39,%40,%41,%42,%43,%44,%45,%46,%47,%48,%49,%50,%51,%52,%53,%54,%55,%56,%57,%58,%59,%60,%61,%62,%63,%64,%65,%66,%67,%68,%69,%70,%71,%72,%73,%74,%75,%76,%77,%78,%79,%80,%81,%82,%83,%84,%85,%86,%87,%88,%89,%90,%91,%92,%93,%94,%95}"
  asm volatile("{\n.reg .pred p, q;\n.reg .b64 a, b;\nsetp.ne.b32 p, %98, 0;\nsetp.eq.b32 q, 0, 0;\nmov.b64 a, {%96, 0x40000040};\nmov.b64 b, {%97, 0x40000040};\n"
               "wgmma.mma_async.sync.aligned.m64n192k16.f32.bf16.bf16 " R_ ", a, b, p, 1, 1, 0, 1;\nadd.s64 a, a, 2;\nadd.s64 b, b, 128;\n"
               "wgmma.mma_async.sync.aligned.m64n192k16.f32.bf16.bf16 " R_ ", a, b, q, 1, 1, 0, 1;\nadd.s64 a, a, 2;\nadd.s64 b, b, 128;\n"
               "wgmma.mma_async.sync.aligned.m64n192k16.f32.bf16.bf16 " R_ ", a, b, q, 1, 1, 0, 1;\nadd.s64 a, a, 2;\nadd.s64 b, b, 128;\n"
               "wgmma.mma_async.sync.aligned.m64n192k16.f32.bf16.bf16 " R_ ", a, b, q, 1, 1, 0, 1;\n}\n"
               : "+f"(d[0]), "+f"(d[1]), "+f"(d[2]), "+f"(d[3]), "+f"(d[4]), "+f"(d[5]), "+f"(d[6]), "+f"(d[7]), "+f"(d[8]), "+f"(d[9]), "+f"(d[10]), "+f"(d[11]), "+f"(d[12]), "+f"(d[13]), "+f"(d[14]), "+f"(d[15]), "+f"(d[16]), "+f"(d[17]), "+f"(d[18]), "+f"(d[19]), "+f"(d[20]), "+f"(d[21]), "+f"(d[22]), "+f"(d[23]), "+f"(d[24]), "+f"(d[25]), "+f"(d[26]), "+f"(d[27]), "+f"(d[28]), "+f"(d[29]), "+f"(d[30]), "+f"(d[31]), "+f"(d[32]), "+f"(d[33]), "+f"(d[34]), "+f"(d[35]), "+f"(d[36]), "+f"(d[37]), "+f"(d[38]), "+f"(d[39]), "+f"(d[40]), "+f"(d[41]), "+f"(d[42]), "+f"(d[43]), "+f"(d[44]), "+f"(d[45]), "+f"(d[46]), "+f"(d[47]), "+f"(d[48]), "+f"(d[49]), "+f"(d[50]), "+f"(d[51]), "+f"(d[52]), "+f"(d[53]), "+f"(d[54]), "+f"(d[55]), "+f"(d[56]), "+f"(d[57]), "+f"(d[58]), "+f"(d[59]), "+f"(d[60]), "+f"(d[61]), "+f"(d[62]), "+f"(d[63]), "+f"(d[64]), "+f"(d[65]), "+f"(d[66]), "+f"(d[67]), "+f"(d[68]), "+f"(d[69]), "+f"(d[70]), "+f"(d[71]), "+f"(d[72]), "+f"(d[73]), "+f"(d[74]), "+f"(d[75]), "+f"(d[76]), "+f"(d[77]), "+f"(d[78]), "+f"(d[79]), "+f"(d[80]), "+f"(d[81]), "+f"(d[82]), "+f"(d[83]), "+f"(d[84]), "+f"(d[85]), "+f"(d[86]), "+f"(d[87]), "+f"(d[88]), "+f"(d[89]), "+f"(d[90]), "+f"(d[91]), "+f"(d[92]), "+f"(d[93]), "+f"(d[94]), "+f"(d[95])
               : "r"(da), "r"(db), "n"(scale_d));
#undef R_
}
template <int scale_d> __device__ __forceinline__ void wgmma4_n128(float* d, uint32_t da, uint32_t db) {
#define R_ "{%0,%1,%2,%3,%4,%5,%6,%7,%8,%9,%10,%11,%12,%13,%14,%15,%16,%17,%18,%19,%20,%21,%22,%23,%24,%25,%26,%27,%28,%29,%30,%31,%32,%33,%34,%35,%36,%37,%38,%39,%40,%41,%42,%43,%44,%45,%46,%47,%48,%49,%50,%51,%52,%53,%54,%55,%56,%57,%58,%59,%60,%61,%62,%63}"
  asm volatile("{\n.reg .pred p, q;\n.reg .b64 a, b;\nsetp.ne.b32 p, %66, 0;\nsetp.eq.b32 q, 0, 0;\nmov.b64 a, {%64, 0x40000040};\nmov.b64 b, {%65, 0x40000040};\n"
               "wgmma.mma_async.sync.aligned.m64n128k16.f32.bf16.bf16 " R_ ", a, b, p, 1, 1, 0, 1;\nadd.s64 a, a, 2;\nadd.s64 b, b, 128;\n"
               "wgmma.mma_async.sync.aligned.m64n128k16.f32.bf16.bf16 " R_ ", a, b, q, 1, 1, 0, 1;\nadd.s64 a, a, 2;\nadd.s64 b, b, 128;\n"
               "wgmma.mma_async.sync.aligned.m64n128k16.f32.bf16.bf16 " R_ ", a, b, q, 1, 1, 0, 1;\nadd.s64 a, a, 2;\nadd.s64 b, b, 128;\n"
               "wgmma.mma_async.sync.aligned.m64n128k16.f32.bf16.bf16 " R_ ", a, b, q, 1, 1, 0, 1;\n}\n"
               : "+f"(d[0]), "+f"(d[1]), "+f"(d[2]), "+f"(d[3]), "+f"(d[4]), "+f"(d[5]), "+f"(d[6]), "+f"(d[7]), "+f"(d[8]), "+f"(d[9]), "+f"(d[10]), "+f"(d[11]), "+f"(d[12]), "+f"(d[13]), "+f"(d[14]), "+f"(d[15]), "+f"(d[16]), "+f"(d[17]), "+f"(d[18]), "+f"(d[19]), "+f"(d[20]), "+f"(d[21]), "+f"(d[22]), "+f"(d[23]), "+f"(d[24]), "+f"(d[25]), "+f"(d[26]), "+f"(d[27]), "+f"(d[28]), "+f"(d[29]), "+f"(d[30]), "+f"(d[31]), "+f"(d[32]), "+f"(d[33]), "+f"(d[34]), "+f"(d[35]), "+f"(d[36]), "+f"(d[37]), "+f"(d[38]), "+f"(d[39]), "+f"(d[40]), "+f"(d[41]), "+f"(d[42]), "+f"(d[43]), "+f"(d[44]), "+f"(d[45]), "+f"(d[46]), "+f"(d[47]), "+f"(d[48]), "+f"(d[49]), "+f"(d[50]), "+f"(d[51]), "+f"(d[52]), "+f"(d[53]), "+f"(d[54]), "+f"(d[55]), "+f"(d[56]), "+f"(d[57]), "+f"(d[58]), "+f"(d[59]), "+f"(d[60]), "+f"(d[61]), "+f"(d[62]), "+f"(d[63])
               : "r"(da), "r"(db), "n"(scale_d));
#undef R_
}
template <int scale_d> __device__ __forceinline__ void wgmma_n32(float* d, uint64_t descA, uint64_t descB) {
  asm volatile("{\n.reg .pred p;\nsetp.ne.b32 p, %18, 0;\n"
               "wgmma.mma_async.sync.aligned.m64n32k16.f32.bf16.bf16 {%0,%1,%2,%3,%4,%5,%6,%7,%8,%9,%10,%11,%12,%13,%14,%15}, %16, %17, p, 1, 1, 0, 1;\n}\n"
               : "+f"(d[0]), "+f"(d[1]), "+f"(d[2]), "+f"(d[3]), "+f"(d[4]), "+f"(d[5]), "+f"(d[6]), "+f"(d[7]), "+f"(d[8]), "+f"(d[9]), "+f"(d[10]), "+f"(d[11]), "+f"(d[12]), "+f"(d[13]), "+f"(d[14]), "+f"(d[15])
               : "l"(descA), "l"(descB), "n"(scale_d));
}
template <int scale_d, int tnsp_a> __device__ __forceinline__ void wgmma_n40(float* d, uint64_t descA, uint64_t descB) {
  asm volatile("{\n.reg .pred p;\nsetp.ne.b32 p, %22, 0;\n"
               "wgmma.mma_async.sync.aligned.m64n40k16.f32.bf16.bf16 {%0,%1,%2,%3,%4,%5,%6,%7,%8,%9,%10,%11,%12,%13,%14,%15,%16,%17,%18,%19}, %20, %21, p, 1, 1, %23, 1;\n}\n"
               : "+f"(d[0]), "+f"(d[1]), "+f"(d[2]), "+f"(d[3]), "+f"(d[4]), "+f"(d[5]), "+f"(d[6]), "+f"(d[7]), "+f"(d[8]), "+f"(d[9]), "+f"(d[10]), "+f"(d[11]), "+f"(d[12]), "+f"(d[13]), "+f"(d[14]), "+f"(d[15]), "+f"(d[16]), "+f"(d[17]), "+f"(d[18]), "+f"(d[19])
               : "l"(descA), "l"(descB), "n"(scale_d), "n"(tnsp_a));
}
template <int scale_d> __device__ __forceinline__ void wgmma_n40_rs(float* d, const uint32_t* a, uint64_t descB) {
  asm volatile("{\n.reg .pred p;\nsetp.ne.b32 p, %25, 0;\n"
               "wgmma.mma_async.sync.aligned.m64n40k16.f32.bf16.bf16 {%0,%1,%2,%3,%4,%5,%6,%7,%8,%9,%10,%11,%12,%13,%14,%15,%16,%17,%18,%19}, {%20,%21,%22,%23}, %24, p, 1, 1, 1;\n}\n"
               : "+f"(d[0]), "+f"(d[1]), "+f"(d[2]), "+f"(d[3]), "+f"(d[4]), "+f"(d[5]), "+f"(d[6]), "+f"(d[7]), "+f"(d[8]), "+f"(d[9]), "+f"(d[10]), "+f"(d[11]), "+f"(d[12]), "+f"(d[13]), "+f"(d[14]), "+f"(d[15]), "+f"(d[16]), "+f"(d[17]), "+f"(d[18]), "+f"(d[19])
               : "r"(a[0]), "r"(a[1]), "r"(a[2]), "r"(a[3]), "l"(descB), "n"(scale_d));
}
__device__ __forceinline__ uint64_t make_desc(uint32_t addr, uint32_t lbo_bytes, uint32_t sbo_bytes) {
  return (uint64_t)((addr & 0x3FFFF) >> 4) | ((uint64_t)(lbo_bytes >> 4) << 16) | ((uint64_t)(sbo_bytes >> 4) << 32) | (1ull << 62);
}

__device__ __forceinline__ void ldsm_x4(uint32_t addr, uint32_t& r0, uint32_t& r1, uint32_t& r2, uint32_t& r3) {
  asm volatile("ldmatrix.sync.aligned.m8n8.x4.shared.b16 {%0,%1,%2,%3}, [%4];" : "=r"(r0), "=r"(r1), "=r"(r2), "=r"(r3) : "r"(addr) : "memory");
}
__device__ __forceinline__ void ldsm_x4_t(uint32_t addr, uint32_t& r0, uint32_t& r1, uint32_t& r2, uint32_t& r3) {
  asm volatile("ldmatrix.sync.aligned.m8n8.x4.trans.shared.b16 {%0,%1,%2,%3}, [%4];" : "=r"(r0), "=r"(r1), "=r"(r2), "=r"(r3) : "r"(addr) : "memory");
}
__device__ __forceinline__ void stsm_x4(uint32_t addr, uint32_t r0, uint32_t r1, uint32_t r2, uint32_t r3) {
  asm volatile("stmatrix.sync.aligned.m8n8.x4.shared.b16 [%0], {%1,%2,%3,%4};" :: "r"(addr), "r"(r0), "r"(r1), "r"(r2), "r"(r3) : "memory");
}
__device__ __forceinline__ void sts128(uint32_t addr, uint32_t a, uint32_t b, uint32_t c, uint32_t d) {
  asm volatile("st.shared.v4.u32 [%0], {%1,%2,%3,%4};" :: "r"(addr), "r"(a), "r"(b), "r"(c), "r"(d) : "memory");
}
__device__ __forceinline__ float lds32f(uint32_t addr) {
  float v;
  asm volatile("ld.shared.f32 %0, [%1];" : "=f"(v) : "r"(addr) : "memory");
  return v;
}
__device__ __forceinline__ void sts32f(uint32_t addr, float a) {
  asm volatile("st.shared.f32 [%0], %1;" :: "r"(addr), "f"(a) : "memory");
}
__device__ __forceinline__ void mma_bf16(float (&c)[4], uint32_t a0, uint32_t a1, uint32_t a2, uint32_t a3, uint32_t b0, uint32_t b1) {
  asm volatile("mma.sync.aligned.m16n8k16.row.col.f32.bf16.bf16.f32 {%0,%1,%2,%3}, {%4,%5,%6,%7}, {%8,%9}, {%0,%1,%2,%3};"
               : "+f"(c[0]), "+f"(c[1]), "+f"(c[2]), "+f"(c[3]) : "r"(a0), "r"(a1), "r"(a2), "r"(a3), "r"(b0), "r"(b1));
}
__device__ __forceinline__ uint32_t pack_bf16(float lo, float hi) {
  uint32_t r;
  asm("cvt.rn.bf16x2.f32 %0, %1, %2;" : "=r"(r) : "f"(hi), "f"(lo));
  return r;
}
__device__ __forceinline__ float bf_lo(uint32_t v) { return __uint_as_float(v << 16); }
__device__ __forceinline__ float bf_hi(uint32_t v) { return __uint_as_float(v & 0xFFFF0000u); }
__device__ __forceinline__ void split3(float x, uint32_t& h, uint32_t& m, uint32_t& l) {
  h = pack_bf16(x, 0.f); x -= bf_lo(h);
  m = pack_bf16(x, 0.f); x -= bf_lo(m);
  l = pack_bf16(x, 0.f);
}
__device__ __forceinline__ float ex2(float x) { float r; asm("ex2.approx.ftz.f32 %0, %1;" : "=f"(r) : "f"(x)); return r; }
__device__ __forceinline__ float rcp_fast(float x) { float r; asm("rcp.approx.ftz.f32 %0, %1;" : "=f"(r) : "f"(x)); return r; }
__device__ __forceinline__ void red_v4(float* p, float a, float b, float c, float d) {
  asm volatile("red.global.add.v4.f32 [%0], {%1, %2, %3, %4};" :: "l"(p), "f"(a), "f"(b), "f"(c), "f"(d) : "memory");
}
__device__ __forceinline__ uint4 ld_ll(const uint4* p) {
  uint4 v;
  asm volatile("{\n.reg .b64 a, b;\nld.relaxed.gpu.global.v2.b64 {a, b}, [%4];\nmov.b64 {%0, %1}, a;\nmov.b64 {%2, %3}, b;\n}\n"
               : "=r"(v.x), "=r"(v.y), "=r"(v.z), "=r"(v.w) : "l"(p) : "memory");
  return v;
}
__device__ __forceinline__ void st_b64(uint2* p, uint32_t a, uint32_t b) {
  asm volatile("{\n.reg .b64 v;\nmov.b64 v, {%1, %2};\nst.relaxed.gpu.global.b64 [%0], v;\n}\n" :: "l"(p), "r"(a), "r"(b) : "memory");
}
__device__ __forceinline__ void st_b128(uint4* p, uint32_t a, uint32_t b, uint32_t c, uint32_t d) {
  asm volatile("{\n.reg .b128 v;\nmov.b128 v, {%1, %2, %3, %4};\nst.relaxed.gpu.global.b128 [%0], v;\n}\n" :: "l"(p), "r"(a), "r"(b), "r"(c), "r"(d) : "memory");
}
__device__ __forceinline__ uint4 ld_b128(const uint4* p) {
  uint4 v;
  asm volatile("{\n.reg .b128 v;\nld.relaxed.gpu.global.b128 v, [%4];\nmov.b128 {%0, %1, %2, %3}, v;\n}\n" : "=r"(v.x), "=r"(v.y), "=r"(v.z), "=r"(v.w) : "l"(p) : "memory");
  return v;
}

constexpr float LOG2E = 1.4426950408889634f;

struct Params {
  const __nv_bfloat16* x0;
  const __nv_bfloat16* wA_qkv;
  const __nv_bfloat16* wA_o;
  const __nv_bfloat16* wB_qkv;
  const __nv_bfloat16* wB_phi;
  const __nv_bfloat16* wB_o;
  __nv_bfloat16* out;
};

#define ACC_DEF(d, n) _Pragma("unroll") for (int i_ = 0; i_ < (n); i_++) asm volatile("" : "=f"(d[i_]))
#define ACC_FENCE(d, n) _Pragma("unroll") for (int i_ = 0; i_ < (n); i_++) asm volatile("" : "+f"(d[i_]) :: "memory")
#define PIN(a, n) _Pragma("unroll") for (int i_ = 0; i_ < (n); i_++) asm volatile("" : "+f"((a)[i_]))
#define PINU(a, n) _Pragma("unroll") for (int i_ = 0; i_ < (n); i_++) asm volatile("" : "+r"((a)[i_]))

#define STAGE64(acc, off, p0, KIND, SEND) { \
    uint32_t w_[4][4]; \
    _Pragma("unroll") for (int j_ = 0; j_ < 4; j_++) { \
      const int o_ = (off) + j_ * 8; \
      w_[j_][0] = pack_bf16(rs0 * acc[o_ + 0], rs0 * acc[o_ + 1]); \
      w_[j_][1] = pack_bf16(rs1 * acc[o_ + 2], rs1 * acc[o_ + 3]); \
      w_[j_][2] = pack_bf16(rs0 * acc[o_ + 4], rs0 * acc[o_ + 5]); \
      w_[j_][3] = pack_bf16(rs1 * acc[o_ + 6], rs1 * acc[o_ + 7]); \
    } \
    if ((SEND) && hsend) { \
      _Pragma("unroll") for (int j_ = 0; j_ < 4; j_++) { \
        w_[j_][0] = (w_[j_][0] & ~1u) | hbit; \
        st_b128(hbase + lane + ((KIND) * 4 + j_) * 32, w_[j_][0], w_[j_][1], w_[j_][2], w_[j_][3]); \
      } \
    } \
    _Pragma("unroll") for (int j_ = 0; j_ < 4; j_++) \
      stsm_x4((KIND) ? (p0) + (j_ >> 1) * 8192 + (srowoff >> 1) + ((((uint32_t)(j_ & 1) << 5) + lhi) ^ lsw2) \
                     : (p0) + srowoff + ((((uint32_t)j_ << 5) + lhi) ^ lsw), \
              w_[j_][0], w_[j_][1], w_[j_][2], w_[j_][3]); \
  }
#define RW(j) (((j) >> 1) * 4 + ((j) & 1))
__device__ __forceinline__ float rmax16(const float* p) {
  float m[4];
#pragma unroll
  for (int j = 0; j < 4; j++) m[j] = fmaxf(fmaxf(p[RW(j)], p[RW(j + 4)]), fmaxf(p[RW(j + 8)], p[RW(j + 12)]));
  const float r = fmaxf(fmaxf(m[0], m[1]), fmaxf(m[2], m[3]));
  return fmaxf(r, __shfl_xor_sync(0xffffffffu, r, 1));
}
__device__ __forceinline__ float rmin16(const float* p) {
  float m[4];
#pragma unroll
  for (int j = 0; j < 4; j++) m[j] = fminf(fminf(p[RW(j)], p[RW(j + 4)]), fminf(p[RW(j + 8)], p[RW(j + 12)]));
  const float r = fminf(fminf(m[0], m[1]), fminf(m[2], m[3]));
  return fminf(r, __shfl_xor_sync(0xffffffffu, r, 1));
}
__device__ __forceinline__ float exps16(float* o, const float* p, float c, float b) {
  float s[4];
#pragma unroll
  for (int j = 0; j < 16; j++) { o[j] = ex2(fmaf(p[RW(j)], c, b)); if (j < 4) s[j] = o[j]; else s[j & 3] += o[j]; }
  return (s[0] + s[1]) + (s[2] + s[3]);
}
__device__ __forceinline__ void store16(const float* e, float sum, uint32_t dst, uint32_t dsw, int c0) {
  const float inv = rcp_fast(sum + __shfl_xor_sync(0xffffffffu, sum, 1));
#pragma unroll
  for (int j = 0; j < 2; j++)
    sts128(dst + (((c0 + j) << 4) ^ dsw), pack_bf16(e[j * 8] * inv, e[j * 8 + 1] * inv), pack_bf16(e[j * 8 + 2] * inv, e[j * 8 + 3] * inv),
           pack_bf16(e[j * 8 + 4] * inv, e[j * 8 + 5] * inv), pack_bf16(e[j * 8 + 6] * inv, e[j * 8 + 7] * inv));
}
__device__ __forceinline__ void expp16(uint32_t* o, const float* p, float c0, float b0, float c1, float b1) {
#pragma unroll
  for (int j = 0; j < 8; j++) {
    const float c = (j & 1) ? c1 : c0, b = (j & 1) ? b1 : b0;
    o[j] = pack_bf16(ex2(fmaf(p[2 * j], c, b)), ex2(fmaf(p[2 * j + 1], c, b)));
  }
}
__device__ __forceinline__ void extrema(float* m, const float* p, float c0, float c1) {
#pragma unroll
  for (int i = 0; i < 4; i++) {
    const float* q = p + (i >> 1) * 16 + (i & 1) * 2;
    m[(i >> 1) * 4 + (i & 1)] = fminf(fminf(fminf(q[0], q[1]), fminf(q[4], q[5])), fminf(fminf(q[8], q[9]), fminf(q[12], q[13])));
    m[(i >> 1) * 4 + (i & 1) + 2] = fmaxf(fmaxf(fmaxf(q[0], q[1]), fmaxf(q[4], q[5])), fmaxf(fmaxf(q[8], q[9]), fmaxf(q[12], q[13])));
  }
#pragma unroll
  for (int o = 1; o <= 2; o <<= 1)
#pragma unroll
    for (int i = 0; i < 8; i++) { const float x = __shfl_xor_sync(0xffffffffu, m[i], o); m[i] = (i & 2) ? fmaxf(m[i], x) : fminf(m[i], x); }
#pragma unroll
  for (int i = 0; i < 8; i++) m[i] *= ((i & 2) ? -1.f : 1.f) * ((i & 1) ? c1 : c0);
}
#define SCHED_FENCE() asm volatile("pmevent 0;" ::: "memory")

__global__ void __cluster_dims__(2, 1, 1) __launch_bounds__(384, 1)
mega_kernel(const __grid_constant__ CUtensorMap tm_x0, const __grid_constant__ CUtensorMap tm_xo, const __grid_constant__ CUtensorMap tm_os,
            const __grid_constant__ CUtensorMap tm_o, const __grid_constant__ CUtensorMap tm_wf,
            const __grid_constant__ CUtensorMap tm_wqA, const __grid_constant__ CUtensorMap tm_wqB,
            const __grid_constant__ CUtensorMap tm_woA, const __grid_constant__ CUtensorMap tm_woB,
            const __grid_constant__ CUtensorMap tm_phi, const Params prm) {
  extern __shared__ __align__(1024) uint8_t smem_raw[];
  const uint32_t sbase = smem_u32(smem_raw);
  const uint32_t bar_full = sbase + OFF_BAR;
  const uint32_t bar_done = bar_full + 384;
  const uint32_t bar_stat = bar_full + 768, bar_stat2 = bar_full + 776, bar_epi = bar_full + 784, bar_phi = bar_full + 936  ;
  const uint32_t bar_xr = bar_full + 800, bar_lx = bar_full + 808, bar_kvf = bar_full + 816  , bar_stg = bar_full + 832;
  const uint32_t bar_chk = bar_full + 848;
  const uint32_t bar_o0 = bar_full + 904;

  const int warp = __shfl_sync(0xffffffffu, threadIdx.x >> 5, 0), lane = threadIdx.x & 31;
  uint32_t rank;
  asm volatile("mov.u32 %0, %%cluster_ctarank;" : "=r"(rank));
  const int cta = (int)blockIdx.x - NAUX;
  const int cl = cta >> 1;
  const int jj = cl & 7, cc = cl >> 3;
  const int mm = cc * 2 + (int)rank;

#define LOAD_EPOCH() const unsigned epoch = ld_relaxed(&g_flags.epoch.v), ep1 = epoch + 1; (void)epoch
  int budget = 1 << 22;

  if (cta >= 0) {
    {
      const int tx = threadIdx.x;
      const __nv_bfloat16* pf = (tx < 128) ? prm.x0 + (size_t)(mm * 128 + tx) * D_MODEL + jj * 128
                                           : prm.wA_qkv + (size_t)(jj * 128 + (tx & 63)) * 3072 + ((tx - 128) >> 6) * 1024 + jj * 128 + rank * 64;
      if (tx < 320) asm volatile("prefetch.global.L2 [%0];" :: "l"(pf));
      else if (tx == 320) prefetch_tmap(&tm_x0);
      else if (tx == 352) prefetch_tmap(&tm_wqA);
      else if (tx == 383) asm volatile("prefetch.global.L2 [%0];" :: "l"(&g_flags.epoch.v));
    }
    if (elect_one()) {
#pragma unroll
      for (int i = 0; i < 4; i++) {
        const int u = warp * 4 + i;
        mbar_init(bar_full + u * 8, ((u >= 4 && u < 11) || (u > 32 && u != 40)) ? 2 : 1); mbar_init(bar_done + u * 8, 16);
      }
      mbar_init(bar_stat + warp * 16, 0x111111181182ull >> (4 * warp) & 15);
      mbar_init(bar_stat + warp * 16 + 8, 0x111111121811ull >> (4 * warp) & 15);
      mbar_init(bar_chk + 112 + (warp & 7) * 8, 1);
      asm volatile("fence.mbarrier_init.release.cluster;" ::: "memory");
    }
    __syncthreads();
    asm volatile("barrier.cluster.arrive.relaxed.aligned;" ::: "memory");
  }

  if (cta < 0) {
    LOAD_EPOCH();
    const uint32_t buf = sbase + warp * SLOT, bar = sbase + OFF_BAR + warp * 16;
    const uint32_t lsw = (lane & 7) << 4, lhi = (lane >> 4) << 4, lrow = (lane & 15) * 128;
    const bool el = elect_one();
    if (el) {
      mbar_init(bar, 1); mbar_init(bar + 8, 1);
      asm volatile("fence.mbarrier_init.release.cluster;" ::: "memory");
    }
#pragma unroll 1
    for (int rd = 0; rd < (NLAYERS > 1 ? 5 : 2); rd++) {
      if (rd >= 2 && warp >= 8) break;
      const int tk = rd < 2 ? blockIdx.x * 12 + warp : blockIdx.x * 8 + warp;
      const int half = tk & 1;
      const int blk = rd < 2 ? (tk >> 1) * 2 + rd : (4 - rd) * 16 + (tk >> 1);
      const CUtensorMap* tm = rd < 2 ? &tm_wqA : (rd == 2 ? &tm_wqB : &tm_wf);
      const int j0 = (blk & 15) >> 1;
#define AUX_LOAD(n) { const uint32_t d_ = buf + ((n) & 1) * 8192, b_ = bar + ((n) & 1) * 8; const int r_ = kslice(j0, 2 * (n) + half) * 64; \
        mbar_expect_tx(b_, 8192); tma_load_2d(d_, tm, b_, blk * 64, r_); tma_load_2d(d_ + 4096, tm, b_, blk * 64, r_ + 32); }
      if (el) {
        if (rd == 3) { wait_flag(&g_flags.wfready[j0].v, ep1 * 16); fence_proxy_async_global(); }
        AUX_LOAD(0); AUX_LOAD(1);
      }
      __syncwarp();
      float cs[8][4];
#pragma unroll
      for (int i = 0; i < 8; i++) cs[i][0] = cs[i][1] = cs[i][2] = cs[i][3] = 0.f;
#pragma unroll 1
      for (int n = 0; n < 8; n++) {
        const uint32_t tb = buf + (n & 1) * 8192 + lrow;
        mbar_wait(bar + (n & 1) * 8, (n >> 1) & 1);
#pragma unroll
        for (int i = 0; i < 16; i++) {
          uint32_t b0, b1, b2, b3;
          ldsm_x4_t(tb + (i >> 2) * 2048 + (((i & 3) * 32 + lhi) ^ lsw), b0, b1, b2, b3);
          mma_bf16(cs[2 * (i & 3)], 0x3F803F80u, 0x3F803F80u, 0x3F803F80u, 0x3F803F80u, b0, b1);
          mma_bf16(cs[2 * (i & 3) + 1], 0x3F803F80u, 0x3F803F80u, 0x3F803F80u, 0x3F803F80u, b2, b3);
        }
        __syncwarp();
        if (el && n < 6) AUX_LOAD(n + 2);
        __syncwarp();
      }
      if (lane < 4) {
#pragma unroll
        for (int i = 0; i < 8; i++) st_b64(&g_colsum[rd >= 2][blk * 32 + i * 4 + lane][half], __float_as_uint(cs[i][0]), (__float_as_uint(cs[i][1]) & ~3u) | (ep1 & 3));
      }
      __syncwarp();
    }
  } else if (warp >= 8) {
    asm volatile("setmaxnreg.dec.sync.aligned.u32 40;");
    if (warp == 8) {
      const bool el = elect_one();
      cluster_wait();
      if (el) {
#pragma unroll 1
        for (int l = 0; l < NLAYERS; l++) {
          const uint32_t par = l & 1;
          const CUtensorMap* tqk = par ? &tm_wf : &tm_wqA;
          const CUtensorMap* tv = par ? &tm_wqB : &tm_wqA;
          const CUtensorMap* two = par ? &tm_woB : &tm_woA;
          if (l == 1) { LOAD_EPOCH(); wait_flag(&g_flags.wfready[jj].v, ep1 * 16); fence_proxy_async_global(); }
#pragma unroll 1
          for (int u = 0; u < 32; u++) {
            if (u >= 4) mbar_wait_sl(bar_done + (u - 4) * 8, par);
            else if (l) mbar_wait_sl(bar_done + (43 + u + (u >> 1)) * 8, par ^ 1);
            else if (u == 1) __nanosleep(STAG1);
            else if (u == 2) mbar_wait_sl(bar_full, 0);
            const uint32_t fb = bar_full + u * 8;
            const bool res = u < 4 ? (l || u >= 2) : (u < 11 || (u >= 18 && u < 22));
            mbar_expect_tx(fb, res ? QST : QST + SLOT);
            const int row = kslice(jj, u < 4 ? u & 1 : (u < 18 ? u - 2 : (u < 22 ? u - 6 : u - 20))) * 64 + (int)rank * 32;
            const int ps = u < 4 ? u >> 1 : (u >= 18), col = jj * 128 + ps * 64;
            const int c0 = par ? jj * 128 + (ps ? 0 : 1024) : col;
            const uint32_t dst = sbase + (u & 3) * QST + rank * 4096;
            tma_load_2d_mc(dst, tqk, fb, c0, row);
            tma_load_2d_mc(dst + 8192, tqk, fb, c0 + (par ? 64 : 1024), row);
            tma_load_2d_mc(dst + 16384, tv, fb, col + 2048, row);
            if (l == 0 && u < 4) PROFT(473 + u);
          }
#pragma unroll 1
          for (int s = 0; s < 16; s++) {
            if (s < 5) { if (s != 2 && s != 4) mbar_wait_sl(bar_done + (28 + s) * 8, par); }
            else if (s != 14) mbar_wait_sl(bar_done + (27 + s - (s == 15)) * 8, par);
            const uint32_t fb = bar_full + (32 + s) * 8;
            mbar_expect_tx(fb, SLOT);
            tma_load_2d_mc(sbase + rank * 8192 + (uint32_t)((WO_BSLOT >> (4 * s)) & 15) * SLOT, two, fb, jj * 128 + (int)rank * 64, wslice(jj, s) * 64);
            const int ts = s + par;
            if (s >= 5 && ts < 8) {
              mbar_wait_sl(bar_o0, par);
              mbar_expect_tx(bar_chk + 104 + ts * 8, SLOT);
              tma_load_2d(sbase + (uint32_t)((WO_ASLOT(par) >> (4 * ts)) & 15) * SLOT, &tm_o, bar_chk + 104 + ts * 8, wslice(jj, ts) * 64, mm * 128);
            }
          }
        }
      }
      __syncwarp();
    } else if (warp == 9) {
      const bool el = elect_one();
      if (el) {
        PROFT(472);
        tma_load_2d(sbase + OFF_S, &tm_x0, bar_full, jj * 128, mm * 128);
        __nanosleep(STAG1);
        tma_load_2d(sbase + OFF_S + SLOT, &tm_x0, bar_full + 8, jj * 128 + 64, mm * 128);
      }
      __syncwarp();
      LOAD_EPOCH();
#pragma unroll 1
      for (int lp = 0; lp < 4 * NLAYERS; lp++) {
        const int l = lp >> 2, ph = lp & 3;
        if (ph == 3) continue;
        const uint32_t par = l & 1;
        const __nv_bfloat16* pb = g_obuf + (ph >> 1) * 64 + (size_t)(mm * 128 + (ph ? 0 : S_LEN) + (lane & 7) * 16 + (jj & 1) * 8) * D_MODEL + (jj >> 1) * 16;
        const CUtensorMap* tm = lp ? &tm_o : &tm_x0;
        const int row = mm * 128 + ((ph || !l) ? 0 : S_LEN);
        const uint32_t bit = ph ? O_BIT(l) : X_BIT(l - 1);
        const uint32_t slots = ph ? (uint32_t)(WO_ASLOT(par) >> (ph * 32 - 28)) : 0x8769876u;
        const unsigned long long fr = ph == 0 ? 0x06050400000000ull : ph == 1 ? (par ? 0x2120353535351Full : 0x22212035351F1Eull) : (par ? 0x27262524232232ull : 0x27262524233232ull);
        uint32_t rdy = (lp == 0 || (lp & 7) == 1) ? 0xFF : 0;
        mbar_wait_sl(ph ? bar_done + ((uint32_t)fr & 63) * 8 : (l ? bar_done + 47 * 8 : bar_full), ph ? par : (l ? par ^ 1 : 0));
#pragma unroll 1
        for (int i = 0; i < 7; i++) {
          if (!((rdy >> i) & 1)) {
            const unsigned* pp = reinterpret_cast<const unsigned*>(pb + ((jj + i + 1 + ((lane >> 3) & (POLLW - 1))) & 7) * 128);
            if (i == 0) __nanosleep(POLL0);
            unsigned v0 = ld_relaxed(pp);
            __nanosleep(POLLGAP);
            unsigned v1 = ld_relaxed(pp);
            uint32_t no;
#pragma unroll 1
            for (int it = 0; it < (1 << 18); it++) {
              no = __ballot_sync(0xffffffffu, (v0 ^ bit) & 1);
              if (!(no & 0xFF)) break;
              v0 = ld_relaxed(pp);
              no = __ballot_sync(0xffffffffu, (v1 ^ bit) & 1);
              if (!(no & 0xFF)) break;
              v1 = ld_relaxed(pp);
            }
            rdy = ((1 | (no & 0xFF00 ? 0 : 2) | (no & 0xFF0000 ? 0 : 4) | (no >> 24 ? 0 : 8)) & ((1 << POLLW) - 1)) << i;
          }
          if (ph == 1 && i >= 4 + par) continue;
          if (ph || i >= 4) mbar_wait_sl(bar_done + ((uint32_t)(fr >> (8 * i)) & 63) * 8, par);
          if (el) {
            if (i == 0) PROFT(320 + l * 16 + ph);
            const uint32_t cb = bar_chk + (ph & 1) * 112 + i * 8;
            mbar_expect_tx(cb, SLOT);
            tma_load_2d(sbase + ((slots >> (4 * i)) & 15) * SLOT, tm, cb, ((jj + i + 1) & 7) * 128 + (ph >> 1) * 64, row);
          }
          __syncwarp();
        }
        if (ph == 1 && el) mbar_arrive_local(bar_o0);
        if (ph == 0 && el) {
          if (l) { wait_flag(&g_flags.xready[l][mm].v, ep1 * 8); fence_proxy_async_global(); }
#pragma unroll 1
          for (int u = 11; u < 34; u++) {
            if (u == 18) u = 22;
            mbar_wait_sl(bar_done + (u - 4) * 8, par);
            if (u == 32) mbar_expect_tx(bar_xr, 2 * SLOT);
            tma_load_2d(sbase + OFF_RA + (u & 3) * SLOT, tm, u < 32 ? bar_full + u * 8 : bar_xr, kslice(jj, u < 18 ? u - 2 : (u < 32 ? u - 20 : u - 32)) * 64, row);
            if (l == 0 && u < 16 && NLAYERS > 1) {
              if (u == 11) { mbar_expect_tx(bar_phi, SLOT + 8192); tma_load_2d(sbase + OFF_PHI, &tm_phi, bar_phi, 0, jj * 128); }
              else tma_load_2d(sbase + 12 * SLOT + (u - 12) * 4096, &tm_wqB, bar_phi, jj * 128 + ((u - 12) >> 1) * 64, mm * 64 + (u & 1) * 32);
            }
          }
        }
        __syncwarp();
      }
      cluster_wait();
    } else {
      const int hw = warp - 10;
      LOAD_EPOCH();
      const bool el = elect_one();
      cluster_wait();
      if (hw == 0) {
        mbar_wait_sl(bar_full + 8, 0);
        if (lane < 7) prefetch_tmap(lane == 0 ? &tm_os : lane == 1 ? &tm_o : lane == 2 ? &tm_wf : lane == 3 ? &tm_wqB : lane == 4 ? &tm_woA : lane == 5 ? &tm_woB : &tm_phi);
        if (lane < 4) asm volatile("prefetch.global.L2 [%0];" :: "l"(prm.wB_phi + jj * 4096 + mm * 256 + lane * 64));
#pragma unroll 1
        for (int i = 0; i < 8; i++) {
          asm volatile("prefetch.global.L2 [%0];" :: "l"(prm.wB_qkv + (size_t)(mm * 64 + (i & 3) * 16 + (lane >> 1)) * 3072 + (i >> 2) * 1024 + jj * 128 + (lane & 1) * 64));
          __nanosleep(PFGAP);
        }
      } else {
#pragma unroll 1
        for (int b = 0; b < 2; b++) {
          float4* z = reinterpret_cast<float4*>(g_kv[b] + (jj * 4) * KVH + mm * (4 * KVH / 16)) + lane;
#pragma unroll
          for (int i = 0; i < 5; i++) z[i * 32] = make_float4(0.f, 0.f, 0.f, 0.f);
        }
#pragma unroll 1
        for (int i = 0; i < 16; i++) {
          const int b = i >> 2;
          const uint32_t v = (b == 0 ? O_BIT(0) : b == 1 ? X_BIT(0) : (NLAYERS > 2 ? 1u : ep1)) + 1;
          uint4* p = b < 2 ? reinterpret_cast<uint4*>(g_obuf + (size_t)(b * S_LEN + mm * 128 + (i & 3) * 32 + (lane >> 3) * 8) * D_MODEL + jj * 128 + (b ? 0 : 64)) + (lane & 7)
                           : g_halo + (size_t)(mm * 8 + jj) * 512 + (i - 8) * 32 + 256 + lane;
          *p = make_uint4(v, v, v, v);
        }
        fence_proxy_async_global();
      }
      __syncwarp();
      uint32_t chkp = 0;
#pragma unroll 1
      for (int lp = 0; lp < 4 * NLAYERS; lp++) {
        const int l = lp >> 2, ph = lp & 3;
        if (ph >= 2 + hw) continue;
        const uint32_t par = l & 1;
        int lane; asm volatile("mov.u32 %0, %%laneid;" : "=r"(lane));
        if (hw) {
          const uint32_t bit = ph ? O_BIT(l) : X_BIT(l - 1);
          const uint32_t slots = ph ? (uint32_t)(WO_ASLOT(par) >> (ph * 32 - 28)) : 0x8769876u;
#pragma unroll 1
          for (int c = 0; c < 7; c++) {
            const uint32_t tile = sbase + ((slots >> (4 * c)) & 15) * SLOT;
            const int cb = c + (ph & 1) * 14;
#pragma unroll 1
            for (int it = 0; it < (1 << 12); it++) {
              mbar_wait_sl(bar_chk + cb * 8, (chkp >> cb) & 1);
              chkp ^= 1u << cb;
              if (el && c == 0) PROFT(ph == 1 ? 480 + l * 2 : 488 + l * 2 + (ph >> 1));
              if (lp == 0) break;
              uint32_t a1 = 1, o1 = 0;
#pragma unroll
              for (int i = 0; i < 16; i++) {
                uint32_t w;
                asm volatile("ld.shared.u32 %0, [%1];" : "=r"(w) : "r"(tile + i * 1024 + (lane & 7) * 132 + (lane >> 3) * 32) : "memory");
                a1 &= w; o1 |= w;
              }
              if (__all_sync(0xffffffffu, ((bit ? a1 : ~o1) & 1) != 0)) break;
              if (el) {
                fence_proxy_async_smem();
                mbar_expect_tx(bar_chk + cb * 8, SLOT);
                tma_load_2d(tile, &tm_o, bar_chk + cb * 8, ((jj + c + 1) & 7) * 128 + (ph >> 1) * 64, mm * 128 + (ph ? 0 : S_LEN));
                RETRY_COUNT();
              }
              __syncwarp();
            }
            if (el) mbar_arrive_local(bar_full + (c + (ph ? 25 + ph * 8 : 4)) * 8);
            __syncwarp();
          }
          if (ph) continue;
#pragma unroll 1
          for (int hp = 0; hp < 2; hp++) {
            const uint4* src = reinterpret_cast<const uint4*>(g_colsum[par][jj * 64 + hp * 32 + lane]);
            uint32_t bad;
            int it = 0;
            float c[6];
            do {
              bad = 0;
#pragma unroll
              for (int p = 0; p < 3; p++) {
                const uint4 v = ld_ll(src + ((par && p < 2) ? (hp ? -32 : 512) + p * 32 : p * 512));
                bad |= (v.y ^ ep1) | (v.w ^ ep1);
                c[2 * p] = __uint_as_float(v.x) + __uint_as_float(v.z); c[2 * p + 1] = __uint_as_float(v.y) + __uint_as_float(v.w);
              }
              bad &= 3;
              if (bad) __nanosleep(300);
            } while (bad && ++it < (1 << 16));
#pragma unroll
            for (int p = 0; p < 6; p++) {
              uint32_t h, m, lo;
              split3(c[p], h, m, lo);
              sts128(sbase + OFF_LNB + hp * 4096 + (p >> 1) * 1024 + lane * 32 + (p & 1) * 16, h | (m << 16), h | (lo << 16), h | (m << 16), lo | (m << 16));
            }
            fence_proxy_async_smem();
            __syncwarp();
            if (el) { mbar_arrive_local(hp ? bar_stat2 : bar_stat); if (hp == 0) PROFT(324 + l * 16); }
            __syncwarp();
          }
          continue;
        } else if (ph == 0) {
          mbar_wait_sl(bar_done + 24, par);
          const uint4* sp = reinterpret_cast<const uint4*>(g_stats + (size_t)(mm * 128) * 8) + lane;
#pragma unroll 1
          for (int hf = 0; hf < 4; hf++) {
            uint4 v[4];
            uint32_t bad;
            int it = 0;
            do {
              bad = 0;
#pragma unroll
              for (int i = 0; i < 4; i++) { v[i] = ld_ll(sp + (hf * 4 + i) * 32); bad |= (v[i].y ^ STAT_TAG(l)) | (v[i].w ^ STAT_TAG(l)); }
              bad &= 3;
              if (bad) __nanosleep(200);
            } while (bad && ++it < (1 << 16));
            __syncwarp();
            float mean = 0.f, m2 = 0.f;
#pragma unroll
            for (int i = 0; i < 4; i++) {
              float a = __uint_as_float(v[i].x) + __uint_as_float(v[i].z);
              a += __shfl_xor_sync(0xffffffffu, a, 1); a += __shfl_xor_sync(0xffffffffu, a, 2);
              a *= 0.125f;
              const float e0 = __uint_as_float(v[i].x) - a, e1 = __uint_as_float(v[i].z) - a;
              float q = fmaf(fmaf(e0, e0, e1 * e1), 128.f, __uint_as_float(v[i].y) + __uint_as_float(v[i].w));
              q += __shfl_xor_sync(0xffffffffu, q, 1); q += __shfl_xor_sync(0xffffffffu, q, 2);
              if ((lane & 3) == i) { mean = a; m2 = q; }
            }
            const uint32_t row = hf * 32 + (lane & 3) * 8 + (lane >> 2);
            uint32_t h, m, lo;
            split3(-0.5f * mean, h, m, lo);
            sts128(sbase + OFF_LNA + row * 16, h | (h << 16), m | (h << 16), lo | (m << 16), m | (lo << 16));
            sts32f(sbase + OFF_ST + row * 4, rsqrtf(m2 * (1.f / 1024.f) + 1e-5f));
          }
          fence_proxy_async_smem();
          __syncwarp();
          if (el) { mbar_arrive_local(bar_stat); PROFT(323 + l * 16); }
          __syncwarp();
#pragma unroll 1
          for (int i = 0; i < 8 - 4 * l; i++) {
            asm volatile("prefetch.global.L2 [%0];" :: "l"(i < 4 ? (l ? prm.wB_o : prm.wA_o) + (size_t)cta * 8192 + i * 2048 + lane * 64
                                                                 : prm.wB_qkv + (size_t)(cta * 8 + (i - 4) * 2 + (lane >> 4)) * 3072 + 2048 + (lane & 15) * 64));
            __nanosleep(PFGAP);
          }
          continue;
        }
        {
          {
            if (l & 1)
#pragma unroll 1
            for (int h = 0; h < 2; h++) {
              asm volatile("bar.sync %0, 288;" :: "r"(BAR_KV + h) : "memory");
              __syncwarp();
              PROFT(331 + l * 16 + h);
              if (lane < 16) signal_release(&g_flags.kvready[(l & 2) + h][jj][lane].v);
              const unsigned* kf = &g_flags.kvready[(l & 2) + h][jj][mm].v;
              unsigned v0 = ld_relaxed(kf);
              __nanosleep(150);
              unsigned v1 = ld_relaxed(kf);
#pragma unroll 1
              for (int it = 0; it < (1 << 18); it++) {
                if (v0 == ep1 * 16) break;
                v0 = ld_relaxed(kf);
                if (v1 == ep1 * 16) break;
                v1 = ld_relaxed(kf);
              }
              fence_acquire();
              __syncwarp();
              if (el) { mbar_arrive_local(bar_kvf + h * 8); PROFT(333 + l * 16 + h); }
              __syncwarp();
            }
          }
#pragma unroll 1
          for (uint32_t ev = l == NLAYERS - 1 ? 0x8u : (l == 0 ? 0x83654u : 0x83u); ev != 8; ev >>= 4) {
            const int e = ev & 15;
            asm volatile("bar.sync %0, 288;" :: "r"((0xFECA987 >> (4 * e)) & 15) : "memory");
            if (el) {
              if (e < 4) {
                PROFT(325 + l * 16 + e);
                tma_store_2d(&tm_o, sbase + 11 * SLOT, jj * 128 + 64, mm * 128 + S_LEN);
              } else {
                if (e == 5) mbar_expect_tx(bar_phi + 8, SLOT);
#pragma unroll 1
                for (int i = 0; i < 4; i++) {
                  const uint32_t a = sbase + (e > 4 ? 10 : 12) * SLOT + i * 4096;
                  const int c0 = (e > 4 ? 1024 : 0) + jj * 128 + (i >> 1) * 64, c1 = mm * 64 + (i & 1) * 32;
                  if (e == 5) tma_load_2d(a, &tm_wqB, bar_phi + 8, c0, c1); else tma_store_2d(&tm_wf, a, c0, c1);
                }
                if (e != 5) {
                  asm volatile("cp.async.bulk.commit_group;\ncp.async.bulk.wait_group.read 0;" ::: "memory");
                  mbar_arrive_local(bar_phi + (e - 4) * 4);
                }
              }
              if ((0x48 >> e) & 1) {
                bulk_commit_wait();
                signal_release(e == 6 ? &g_flags.wfready[jj].v : &g_flags.xready[l + 1][mm].v);
              }
              if (e == 3) PROFT(330 + l * 16);
              if (e == 6) PROFT(335);
            }
            __syncwarp();
          }
        }
      }
    }
    cluster_sync();
  } else {
    asm volatile("setmaxnreg.inc.sync.aligned.u32 232;");
    LOAD_EPOCH();
    const int wg = warp >> 2;
    const int r0 = warp * 16;
    const uint32_t pK = sbase + OFF_S, pV = sbase + OFF_S + SLOT;
#define PMASKS(on, bit) const uint32_t pm0 = ((on) && t == (g & 3) && (g >> 2) == (g & 1)), pm1 = ((on) && t == (g & 3) && (g >> 2) != (g & 1)), pbit = (bit)
#define PBIT0(w) (((w) & ~pm0) | (pbit & pm0))
#define PBIT1(w) (((w) & ~pm1) | (pbit & pm1))
#define LANE_CONSTS() \
    int lane; asm volatile("mov.u32 %0, %%laneid;" : "=r"(lane)); \
    const int g = lane >> 2, t = lane & 3; \
    const uint32_t srowoff = (r0 + (lane & 15)) * 128, lsw = (lane & 7) << 4, lhi = (lane >> 4) << 4, lsw2 = (lane & 6) << 3; \
    (void)g; (void)t; (void)srowoff; (void)lsw; (void)lhi; (void)lsw2;
    uint32_t stgp = 0, peer;
    asm volatile("mapa.shared::cluster.u32 %0, %1, %2;" : "=r"(peer) : "r"(sbase), "r"(rank ^ 1));
    peer -= sbase;
    const uint32_t dA0 = (((sbase & 0x3FFFF) + wg * 8192) >> 4) | 0x10000u, dB0 = ((sbase & 0x3FFFF) >> 4) | 0x2000000u;
    cluster_wait();
#define STG_ARRIVE() { __syncwarp(); if (elect_one()) mbar_arrive_local(bar_stg); }
#define STG_WAIT() { mbar_wait(bar_stg, stgp); stgp ^= 1; }
#define PROFS() do {} while (0)
#define REL(addr) { if (elect_one()) { mbar_arrive_local(addr); asm volatile("mbarrier.arrive.shared::cluster.b64 _, [%0];" :: "r"((addr) + peer) : "memory"); } }
#define QSTEP(ACC, DA, SC, PRE) { \
      const uint32_t da = (DA), db = dB0 + (ub & 0x18) * (QST >> 7); \
      mbar_wait(ub, par); \
      PRE; \
      wgmma_fence(); \
      wgmma4_n192<SC>(ACC, da, db); \
      wgmma_commit(); PROFS(); }
#define QREL() { wgmma_wait<1>(); REL(ub + 376); ub += 8; }
#define RA_CUR (dA0 + (OFF_RA >> 4) + (ub & 0x18) * (SLOT >> 7))
#define PUMP1() { QSTEP(S1, RA_CUR, 1, {}); QREL(); }
#define PUMP0() { PUMP1(); SCHED_FENCE(); }
#define PUMP() if (h == 0) PUMP1()
#define WSTEP() { \
      const uint32_t s4 = (ub - bar_full - 256) >> 1; \
      const uint32_t da = dA0 + (((uint32_t)(WO_ASLOT(par) >> s4) & 15) << 10), db = dB0 + (((uint32_t)(WO_BSLOT >> s4) & 15) << 10); \
      mbar_wait(ub, par); \
      wgmma_fence(); \
      wgmma4_n128<1>(S1, da, db); \
      wgmma_commit(); PROFS(); \
      wgmma_wait<1>(); \
      if (s4) REL(ub + 376); \
      ub += 8; }
#define PUMPS(n) { _Pragma("unroll 1") for (int i_ = 0; i_ < (n); i_++) PUMP1(); }
#define SITE(n) { if ((BMASK >> (n)) & 1) PUMP1(); SCHED_FENCE(); }
#define LNSTEP(ACC, hh) { wgmma_fence(); wgmma_n192<1, 0>(ACC, make_desc(sbase + OFF_LNA + wg * 1024, 0, 128) ^ (1ull << 62), make_desc(sbase + OFF_LNB + (hh) * 4096, 0, 128) ^ (1ull << 62)); }
#define DRAIN_A(ACC, PMP) { \
      LANE_CONSTS(); \
      STAGE64(ACC, 64, pV, 1, 1); \
      PMP; \
      STAGE64(ACC, 32, pK, 0, 1); \
      STG_ARRIVE(); \
      _Pragma("unroll") for (int i_ = 0; i_ < 16; i_++) qa[i_] = pack_bf16(ACC[2 * i_], ACC[2 * i_ + 1]); \
      PINU(qa, 16); }
#define DRAIN_B(ACC) { \
      LANE_CONSTS(); \
      STAGE64(ACC, 64, pV, 1, 0); \
      _Pragma("unroll") for (int i_ = 0; i_ < 64; i_++) st[i_] = ACC[i_]; \
      PIN(st, 64); }
#define WARP_STORE(tm, tile, col, row) { fence_proxy_async_smem(); __syncwarp(); \
      if (elect_one()) { tma_store_2d(tm, (tile) + r0 * 128, col, (row) + r0); asm volatile("cp.async.bulk.commit_group;" ::: "memory"); } __syncwarp(); }
#define PUBLISH_O() WARP_STORE(&tm_os, pO, jj * 128 + h * 64, mm * 128)
#define X_OUT(pc, on) { \
      PMASKS(on, X_BIT(l)); \
      _Pragma("unroll") for (int j = (pc) * 4; j < (pc) * 4 + 4; j++) \
        stsm_x4(pK + (pc) * SLOT + srowoff + ((((uint32_t)(j & 3) << 5) + lhi) ^ lsw), \
                PBIT0(pack_bf16(S1[j * 8 + 0], S1[j * 8 + 1])), PBIT0(pack_bf16(S1[j * 8 + 2], S1[j * 8 + 3])), \
                PBIT1(pack_bf16(S1[j * 8 + 4], S1[j * 8 + 5])), PBIT1(pack_bf16(S1[j * 8 + 6], S1[j * 8 + 7]))); }
#define REST_P1(SKEW, HOOK) { \
      mbar_wait(bar_stat2, par); \
      LNSTEP(S1, 1); \
      _Pragma("unroll 1") while (ub < bar_full + 256) { \
        if (ub == bar_full + 256 - 8 * (SKEW) && wg == 0) bar_sync<BAR_SKEW, 256>(); \
        QSTEP(S1, RA_CUR, 1, {}); \
        if (ub == bar_full + 248 && wg == 1) bar_arrive<BAR_SKEW, 256>(); \
        QREL(); \
      } \
      hbase += 256; \
      HOOK; \
      mbar_wait(bar_done + (31 - (SKEW)) * 8, par);        \
      wgmma_wait<0>(); \
      ACC_FENCE(S1, 96); \
      REL(bar_done + 31 * 8); \
      PROF(13); }
#define FOLD(tile, rd) { \
          LANE_CONSTS(); \
          float d[32]; \
          ACC_DEF(d, 32); \
          mbar_wait(bar_phi + (rd) * 8, 0); \
          wgmma_fence(); \
          _Pragma("unroll") for (int i = 0; i < 2; i++) { \
            const uint64_t da = make_desc((tile) + wg * 8192 + i * 64, 16, 1024); \
            const uint64_t db = make_desc(sbase + OFF_PHI + wg * 4096 + i * 2048, 16, 512) ^ (3ull << 62); \
            wgmma_n32<0>(d + i * 16, da, db); wgmma_n32<1>(d + i * 16, da + 2, db + 64); \
          } \
          wgmma_commit(); \
          PUMP0(); \
          ACC_FENCE(d, 32); \
          bar_wg(wg); \
          _Pragma("unroll") for (int i = 0; i < 4; i++) { \
            const float* x = d + (i & 1) * 8 + (i >> 1) * 2; \
            if (rd) sts128((tile) + wg * 8192 + ((warp & 3) * 16 + (i >> 1) * 8 + g) * 128 + (((2 * t + (i & 1)) ^ g) << 4), \
                           pack_bf16(x[0], x[1]), pack_bf16(x[4], x[5]), pack_bf16(x[16], x[17]), pack_bf16(x[20], x[21])); \
            else stsm_x4((tile) + srowoff + ((((uint32_t)i << 5) + lhi) ^ lsw), pack_bf16(d[i * 8], d[i * 8 + 1]), pack_bf16(d[i * 8 + 2], d[i * 8 + 3]), \
                         pack_bf16(d[i * 8 + 4], d[i * 8 + 5]), pack_bf16(d[i * 8 + 6], d[i * 8 + 7])); \
          } \
          fence_proxy_async_smem(); \
          bar_arrive<BAR_WF + 3 * (rd), 288>(); }
#define LOAD_X0(base) \
      _Pragma("unroll") for (int j = 0; j < 8; j++) { \
        uint32_t x0, x1, x2, x3; \
        ldsm_x4((base) + (j >> 2) * SLOT + srowoff + ((((uint32_t)(j & 3) << 5) + lhi) ^ lsw), x0, x1, x2, x3); \
        S1[j * 8 + 0] = bf_lo(x0); S1[j * 8 + 1] = bf_hi(x0); S1[j * 8 + 2] = bf_lo(x1); S1[j * 8 + 3] = bf_hi(x1); \
        S1[j * 8 + 4] = bf_lo(x2); S1[j * 8 + 5] = bf_hi(x2); S1[j * 8 + 6] = bf_lo(x3); S1[j * 8 + 7] = bf_hi(x3); \
      }
#define LOAD_X() { \
      wgmma_wait<0>(); \
      mbar_wait(bar_xr, par); \
      LOAD_X0(sbase + OFF_RA); \
      ACC_FENCE(S1, 64); \
      __syncwarp(); if (elect_one()) mbar_arrive_local(bar_lx); }

    float S1[96];
#pragma unroll
    for (int i = 0; i < 64; i++) S1[i] = 0.f;
#pragma unroll 1
    for (int l = 0; l < NLAYERS; l++) {
      const uint32_t par = l & 1;
      bar_wg(wg);
      PROF(0);
      uint32_t ub = bar_full;
      const bool hsend = (warp == 7) && (mm < 15);
      const uint32_t hbit = (NLAYERS > 2) ? (l == 0) : (ep1 & 1);
      float S0[96];
      {
        LANE_CONSTS();
        ACC_DEF(S0, 96);
        QSTEP(S0, dA0 + (OFF_S >> 4), 0, {});
        ub += 8;
        PROF(1);
        if (l == 0) { mbar_wait(ub, 0); LOAD_X0(pK); }
        else { X_OUT(1, false); fence_proxy_async_smem(); }
        SCHED_FENCE();
        {
          float a0 = S1[0], a1 = S1[2], b0 = S1[1], b1 = S1[3];
#pragma unroll
          for (int i = 4; i < 64; i += 4) { a0 += S1[i]; b0 += S1[i + 1]; a1 += S1[i + 2]; b1 += S1[i + 3]; }
          a0 += b0; a1 += b1;
          a0 += __shfl_xor_sync(0xffffffffu, a0, 1); a1 += __shfl_xor_sync(0xffffffffu, a1, 1);
          a0 += __shfl_xor_sync(0xffffffffu, a0, 2); a1 += __shfl_xor_sync(0xffffffffu, a1, 2);
          a0 *= (1.f / 128.f); a1 *= (1.f / 128.f);
          asm volatile("" : "+f"(a0), "+f"(a1));
          bar_wg(wg);
          QSTEP(S0, dA0 + ((OFF_S + SLOT) >> 4), 1, wgmma_wait<0>());
          REL(ub + 376); ub += 8;
          SCHED_FENCE();
          float q0 = 0.f, q1 = 0.f;
          b0 = 0.f; b1 = 0.f;
#pragma unroll
          for (int i = 0; i < 64; i += 4) {
            const float d0 = S1[i] - a0, d1 = S1[i + 1] - a0, d2 = S1[i + 2] - a1, d3 = S1[i + 3] - a1;
            q0 = fmaf(d0, d0, q0); b0 = fmaf(d1, d1, b0); q1 = fmaf(d2, d2, q1); b1 = fmaf(d3, d3, b1);
          }
          q0 += b0; q1 += b1;
          q0 += __shfl_xor_sync(0xffffffffu, q0, 1); q1 += __shfl_xor_sync(0xffffffffu, q1, 1);
          q0 += __shfl_xor_sync(0xffffffffu, q0, 2); q1 += __shfl_xor_sync(0xffffffffu, q1, 2);
          if (t < 2) st_b64(g_stats + (size_t)(mm * 128 + r0 + g + t * 8) * 8 + jj, __float_as_uint(t ? a1 : a0), (__float_as_uint(t ? q1 : q0) & ~3u) | STAT_TAG(l));
        }
        if (l) { asm volatile("cp.async.bulk.wait_group 0;" ::: "memory"); bar_arrive<BAR_O + 3, 288>(); }
        ACC_DEF(S1, 96);
        QSTEP(S1, dA0 + (OFF_S >> 4), 0, {});
        QREL();
        QSTEP(S1, dA0 + ((OFF_S + SLOT) >> 4), 1, {});
        QREL();
#pragma unroll 1
        for (int i = 0; i < 14; i++) {
          QSTEP(S0, RA_CUR, 1, {});
          if (i == 0) PROF(2);
          QREL();
        }
      }
      LANE_CONSTS();
      uint4* hbase = g_halo + (size_t)(mm * 8 + jj) * 512;
      mbar_wait(bar_stat, par);
      LNSTEP(S0, 0);
      wgmma_commit();
      const float rs0 = lds32f(sbase + OFF_ST + (r0 + g) * 4), rs1 = lds32f(sbase + OFF_ST + (r0 + g + 8) * 4);
      PUMP0();
      ACC_FENCE(S0, 96);
      PROF(3);
      if (!par) {
        constexpr uint32_t par = 0;
        uint32_t qa[16];
        DRAIN_A(S0, PUMP0());
#pragma unroll 1
        for (int h = 0; h < 2; h++) {
          const uint32_t pO = sbase + (h ? 3 : 12) * SLOT;
          PROF(4 + h * 12);
          const bool fold = (l == 0 && h == 0 && NLAYERS > 1);
          if (fold) FOLD(pO, 0) else if (h == 0) PUMPS(HPUMP1);
          LANE_CONSTS();
          uint4 hv[8];
#pragma unroll
          for (int i = 0; i < 8; i++) hv[i] = make_uint4(hbit, 0, 0, 0);
          const bool hrec = (warp == 0 && mm > 0);
          if (hrec) {
#pragma unroll
            for (int i = 0; i < 8; i++) hv[i] = ld_b128(hbase + lane - 8 * 512 + i * 32);
          }
          if (h) LOAD_X() else PUMPS(HPUMP2);
          const uint32_t halo = sbase + OFF_HALO;
          STG_WAIT();
          if (warp == 0) {
#pragma unroll 1
            for (int it = 0; it < (1 << 16); it++) {
              uint32_t bad = 0;
#pragma unroll
              for (int i = 0; i < 8; i++) bad |= hv[i].x ^ hbit;
              if (__all_sync(0xffffffffu, (bad & 1) == 0)) break;
#pragma unroll
              for (int i = 0; i < 8; i++) hv[i] = ld_b128(hbase + lane - 8 * 512 + i * 32);
            }
#pragma unroll
            for (int i = 0; i < 8; i++)
              stsm_x4(i < 4 ? halo + srowoff + ((((uint32_t)i << 5) + lhi) ^ lsw)
                            : halo + (srowoff >> 1) + (i >> 1) * 1024 + ((((uint32_t)(i & 1) << 5) + lhi) ^ lsw2), hv[i].x, hv[i].y, hv[i].z, hv[i].w);
            __syncwarp();
          }
          PROF(5 + h * 12);
          const uint32_t kb1 = pK + r0 * 128, vb1 = pV + r0 * 64;
          const uint32_t kb0 = r0 ? kb1 - 2048 : halo, vb0 = r0 ? vb1 - 1024 : halo + 2048;
          const uint32_t vhs = r0 ? 8192 : 1024;
          float s[2][4][4];
          {
            uint32_t kf[2][4][4];
#pragma unroll
            for (int i = 0; i < 8; i++) {
              const int hh = i >> 2, jb = i & 3;
              ldsm_x4(((jb < 2) ? kb0 : kb1) + ((jb & 1) * 8 + (lane & 7)) * 128 + ((hh * 64 + ((lane >> 3) << 4)) ^ lsw), kf[hh][jb][0], kf[hh][jb][1], kf[hh][jb][2], kf[hh][jb][3]);
              s[hh][jb][0] = s[hh][jb][1] = s[hh][jb][2] = s[hh][jb][3] = 0.f;
            }
#pragma unroll
            for (int ks = 0; ks < 2; ks++)
#pragma unroll
              for (int i = 0; i < 8; i++) {
                const int hh = i >> 2, jb = i & 3;
                mma_bf16(s[hh][jb], qa[hh * 8 + ks * 4], qa[hh * 8 + ks * 4 + 1], qa[hh * 8 + ks * 4 + 2], qa[hh * 8 + ks * 4 + 3], kf[hh][jb][ks * 2], kf[hh][jb][ks * 2 + 1]);
              }
          }
          PUMP();
          if (fold) bar_arrive<BAR_WF + 2, 288>();
          PROF(6 + h * 12);
          const bool e = g & 1, hb = (2 * t + (g & 1)) <= g;
          uint32_t vf[2][2][2][4];
#pragma unroll
          for (int i = 0; i < 8; i++) {
            const int hh = i >> 2, ks = (i >> 1) & 1, dp = i & 1;
            ldsm_x4_t((ks ? vb1 + hh * 8192 : vb0 + hh * vhs) + (lane & 15) * 64 + ((dp * 32 + lhi) ^ lsw2), vf[hh][ks][dp][0], vf[hh][ks][dp][1], vf[hh][ks][dp][2], vf[hh][ks][dp][3]);
          }
          float va[2][2], vb[2][2], mx[2][2];
#pragma unroll
          for (int hh = 0; hh < 2; hh++) {
            va[hh][0] = e ? s[hh][1][1] : s[hh][1][0];
            vb[hh][0] = hb ? (e ? s[hh][2][1] : s[hh][2][0]) : (e ? s[hh][0][1] : s[hh][0][0]);
            va[hh][1] = e ? s[hh][2][3] : s[hh][2][2];
            vb[hh][1] = hb ? (e ? s[hh][3][3] : s[hh][3][2]) : (e ? s[hh][1][3] : s[hh][1][2]);
          }
          if (warp == 0 && mm == 0) {
#pragma unroll
            for (int hh = 0; hh < 2; hh++) { va[hh][0] = -INFINITY; if (!hb) { vb[hh][0] = -INFINITY; vb[hh][1] = -INFINITY; } }
          }
#pragma unroll
          for (int i = 0; i < 4; i++) mx[i >> 1][i & 1] = fmaxf(va[i >> 1][i & 1], vb[i >> 1][i & 1]);
#pragma unroll
          for (int o = 1; o <= 2; o <<= 1)
#pragma unroll
            for (int i = 0; i < 4; i++) mx[i >> 1][i & 1] = fmaxf(mx[i >> 1][i & 1], __shfl_xor_sync(0xffffffffu, mx[i >> 1][i & 1], o));
          const float sc0 = rs0 * (0.17677669529663687f * LOG2E), sc1 = rs1 * (0.17677669529663687f * LOG2E);
#pragma unroll
          for (int i = 0; i < 4; i++) {
            const float sc = (i & 1) ? sc1 : sc0, m = mx[i >> 1][i & 1];
            va[i >> 1][i & 1] = ex2((va[i >> 1][i & 1] - m) * sc); vb[i >> 1][i & 1] = ex2((vb[i >> 1][i & 1] - m) * sc);
            mx[i >> 1][i & 1] = va[i >> 1][i & 1] + vb[i >> 1][i & 1];
          }
          if (h == 0 && ASITE) { PIN(&va[0][0], 4); PIN(&vb[0][0], 4); PIN(&mx[0][0], 4); PUMP1(); }
#pragma unroll
          for (int o = 1; o <= 2; o <<= 1)
#pragma unroll
            for (int i = 0; i < 4; i++) mx[i >> 1][i & 1] += __shfl_xor_sync(0xffffffffu, mx[i >> 1][i & 1], o);
          const uint32_t selA = e ? 0x1044 : 0x4410, selB = e ? 0x3244 : 0x4432, selL = hb ? 0x4444 : selB, selH = hb ? selB : 0x4444;
          float o[2][4][4];
          uint32_t pa[2][6];
#pragma unroll
          for (int hh = 0; hh < 2; hh++) {
            const float i0 = rcp_fast(mx[hh][0]), i1 = rcp_fast(mx[hh][1]);
            const uint32_t w0 = pack_bf16(va[hh][0] * i0, vb[hh][0] * i0), w1 = pack_bf16(va[hh][1] * i1, vb[hh][1] * i1);
            pa[hh][0] = __byte_perm(w0, 0, selL); pa[hh][1] = __byte_perm(w0, 0, selA); pa[hh][2] = __byte_perm(w1, 0, selL);
            pa[hh][3] = __byte_perm(w0, 0, selH); pa[hh][4] = __byte_perm(w1, 0, selA); pa[hh][5] = __byte_perm(w1, 0, selH);
#pragma unroll
            for (int dj = 0; dj < 4; dj++) { o[hh][dj][0] = o[hh][dj][1] = o[hh][dj][2] = o[hh][dj][3] = 0.f; }
          }
          PROF(7 + h * 12);
#pragma unroll
          for (int i = 0; i < 8; i++) mma_bf16(o[i >> 2][i & 3], pa[i >> 2][0], 0u, pa[i >> 2][1], pa[i >> 2][2], vf[i >> 2][0][(i >> 1) & 1][(i & 1) * 2], vf[i >> 2][0][(i >> 1) & 1][(i & 1) * 2 + 1]);
#pragma unroll
          for (int i = 0; i < 8; i++) mma_bf16(o[i >> 2][i & 3], pa[i >> 2][3], pa[i >> 2][4], 0u, pa[i >> 2][5], vf[i >> 2][1][(i >> 1) & 1][(i & 1) * 2], vf[i >> 2][1][(i >> 1) & 1][(i & 1) * 2 + 1]);
          if (h == 0) PUMP1() else mbar_wait(bar_done + 30 * 8, par);
          if (fold) mbar_wait(bar_phi, 1);
#pragma unroll
          for (int i = 0; i < 4; i++) {
            const int hh = i >> 1, dp = i & 1;
            PMASKS(true, O_BIT(l));
            stsm_x4(pO + srowoff + ((hh * 64 + dp * 32 + lhi) ^ lsw), PBIT0(pack_bf16(o[hh][dp * 2][0], o[hh][dp * 2][1])), PBIT0(pack_bf16(o[hh][dp * 2][2], o[hh][dp * 2][3])),
                    PBIT1(pack_bf16(o[hh][dp * 2 + 1][0], o[hh][dp * 2 + 1][1])), PBIT1(pack_bf16(o[hh][dp * 2 + 1][2], o[hh][dp * 2 + 1][3])));
          }
          PUBLISH_O();
          PROF(11 + h * 12);
          if (h) break;
          if (fold) { PUMPS(FPUMP); FOLD(pK, 1); }
          REST_P1(ASKEW, asm volatile("cp.async.bulk.wait_group.read 0;" ::: "memory"));
          if (fold) mbar_wait(bar_phi + 8, 1);
          DRAIN_A(S1, {});
        }
      } else {
        constexpr uint32_t par = 1;
        float st[64];
        DRAIN_B(S0);
        if (warp < 2) sts128(sbase + OFF_ONES + warp * 512 + lane * 16, 0x3F803F80u, 0x3F803F80u, 0x3F803F80u, 0x3F803F80u);
        const float c0 = rs0 * LOG2E, c1 = rs1 * LOG2E;
#define KV_MMA(vs) { \
          const uint64_t dp = make_desc(wg ? pK : sbase + 12 * SLOT, 16, 1024); \
          const uint64_t dv = (make_desc(sbase + (vs) * SLOT + wg * 8192, OFF_ONES - (vs) * SLOT - wg * 8192, 512) ^ (3ull << 62)); \
          constexpr uint64_t DVS = 64ull - (64ull << 16); \
          STG_WAIT(); \
          wgmma_fence(); \
          _Pragma("unroll") for (int ks = 0; ks < 8; ks++) { if (ks == 0) wgmma_n40<0, 1>(kv, dp, dv); else wgmma_n40<1, 1>(kv, dp + ks * 128, dv + ks * DVS); } \
          wgmma_commit(); }
#define KV_RED(hp) { \
          float* kvg = g_kv[l >> 1] + (jj * 4 + (hp) * 2 + wg) * KVH + ((warp & 3) * 32 + lane) * 4; \
          _Pragma("unroll") for (int i = 0; i < 4; i++) red_v4(kvg + i * 512, kv[i * 4], kv[i * 4 + 1], kv[i * 4 + 2], kv[i * 4 + 3]); \
          if (t == 0) red_v4(kvg + 2048, kv[16], kv[17], kv[18], kv[19]); \
          bar_arrive<BAR_KV + (hp), 288>(); }
#define KV_LOAD(hp) { \
          LANE_CONSTS(); \
          const float4* kvg = reinterpret_cast<const float4*>(g_kv[l >> 1] + (jj * 4 + (hp) * 2 + wg) * KVH) + (warp & 3) * 32 + lane; \
          mbar_wait(bar_kvf + (hp) * 8, l >> 1); \
          PROF(25 + (hp)); \
          _Pragma("unroll") for (int i = 0; i < 4; i++) v[i] = __ldcg(kvg + i * 128); \
          v[4] = __ldcg(kvg + 512 - t); }
#define KV_TILE(pT) { \
          LANE_CONSTS(); \
          const uint32_t e = lane & 7, jt = ((lane >> 1) & 4) + (e >> 1); \
          const uint32_t row = ((((warp >> 1) ^ wg) & 1) << 5) + ((jt & 1) << 4) + ((warp & 1) << 3) + (jt & 6) + (e & 1); \
          const uint32_t kd = (pT) + wg * 8192 + row * 128, ksw = (row & 7) << 4; \
          _Pragma("unroll") for (int i = 0; i < 2; i++) { \
            const float4 a = v[i * 2], b = v[i * 2 + 1]; \
            stsm_x4(kd + ((i * 32 + lhi) ^ ksw), pack_bf16(a.x, a.y), pack_bf16(a.z, a.w), pack_bf16(b.x, b.y), pack_bf16(b.z, b.w)); \
          } \
          stsm_x4(kd + ((64u + lhi) ^ ksw), pack_bf16(v[4].x, 1.f), pack_bf16(v[4].z, 1.f), 0u, 0u); \
          fence_proxy_async_smem(); \
          STG_ARRIVE(); }
#pragma unroll 1
        for (int h = 0; h < 2; h++) {
          PROF(4 + h * 2);
          SITE(0);
          LANE_CONSTS();
          const uint32_t dsw = (uint32_t)(g ^ (2 * t)) << 4, dst = ((t & 2) ? pK : sbase + 12 * SLOT) + (r0 + g) * 128;
          float e[16], f[16];
          float mn0 = rmin16(st);
          asm volatile("" : "+f"(mn0)); SCHED_FENCE();
          float sa = exps16(e, st, -c0, mn0 * c0), mx0 = rmax16(st);
          asm volatile("" : "+f"(sa), "+f"(mx0)); PIN(e, 16); SITE(1);
          if (h) STG_WAIT();
          store16(e, sa, dst, dsw, 4);
          float sb = exps16(f, st, c0, -mx0 * c0), mn1 = rmin16(st + 2);
          asm volatile("" : "+f"(sb), "+f"(mn1)); PIN(f, 16); SITE(2);
          store16(f, sb, dst, dsw, 0);
          float sc = exps16(e, st + 2, -c1, mn1 * c1), mx1 = rmax16(st + 2);
          asm volatile("" : "+f"(sc), "+f"(mx1)); PIN(e, 16); SITE(3);
          store16(e, sc, dst + 1024, dsw, 4);
          float sd = exps16(f, st + 2, c1, -mx1 * c1);
          asm volatile("" : "+f"(sd)); PIN(f, 16); SITE(4);
          store16(f, sd, dst + 1024, dsw, 0);
          PROF(5 + h * 2);
          if (h) break;
          {
            float kv[20];
            ACC_DEF(kv, 20);
            fence_proxy_async_smem();
            STG_ARRIVE();
            KV_MMA(11);
            PUMP0();
            ACC_FENCE(kv, 20);
            KV_RED(0);
            STG_ARRIVE();
          }
#pragma unroll
          for (int i = 0; i < 32; i++) st[i] = st[32 + i];
        }
        float mq[8];
        {
          float4 v[5];
          float kv[20];
          mbar_wait(bar_stat2, par);
          LNSTEP(S1, 1);
          ub = bar_full + 240;
          PUMP1();
          if (wg == 0) bar_sync<BAR_SKEW, 256>();
          QSTEP(S1, RA_CUR, 1, {});
          if (wg == 1) bar_arrive<BAR_SKEW, 256>();
          KV_LOAD(0);
          QREL();
          mbar_wait(bar_done + 30 * 8, par);
          wgmma_wait<0>();
          ACC_FENCE(S1, 96);
          REL(bar_done + 31 * 8);
          PROF(13);
          LANE_CONSTS();
          STAGE64(S1, 64, sbase + 3 * SLOT, 1, 0);
          fence_proxy_async_smem();
          STG_ARRIVE();
#pragma unroll
          for (int i = 0; i < 32; i++) st[i] = S1[i];
          PIN(st, 32);
          PROF(16);
          ACC_DEF(kv, 20);
          KV_MMA(3);
          SCHED_FENCE();
          KV_TILE(pV);
          extrema(mq, st, c0, c1);
          PIN(mq, 8);
          wgmma_wait<0>();
          ACC_FENCE(kv, 20);
          KV_RED(1);
          PROF(17);
        }
#pragma unroll 1
        for (int h = 0; h < 2; h++) {
          const uint32_t pO = sbase + (h ? 3 : 8) * SLOT;
          LANE_CONSTS();
          uint32_t fq[32];
          float4 v[5];
          expp16(fq, st, -c0, mq[0], -c1, mq[1]); expp16(fq + 8, st, c0, mq[2], c1, mq[3]); PINU(fq, 16);
          PROF(18 + h * 14);
          if (h) {
            asm volatile("cp.async.bulk.wait_group.read 0;" ::: "memory");
            uint32_t n;
#pragma unroll 1
            while (ub < bar_full + 8 * FILL) {
              int it = 0;
              do {
                asm volatile("{\n.reg .pred p, q;\nsetp.ne.u32 q, %4, 0;\nmbarrier.test_wait.parity.shared::cta.b64 p, [%1], %2;\nand.pred p, p, q;\n"
                             "barrier.red.popc.aligned.u32 %0, %3, 128, p;\n}\n"
                             : "=r"(n) : "r"((warp & 3) ? ub : bar_kvf + 8), "r"((warp & 3) ? par : l >> 1), "r"(2 + wg), "r"((warp & 3) | (uint32_t)(lane == 0)) : "memory");
                n = __shfl_sync(0xffffffffu, n, 0);
              } while (n == 0 && ++it < (1 << 20));
              if (n & 1) break;
              WSTEP();
            }
            KV_LOAD(1);
          } else {
#pragma unroll
            for (int i = 0; i < 5; i++) v[i] = make_float4(0.f, 0.f, 0.f, 0.f);
          }
          SCHED_FENCE();
          expp16(fq + 16, st + 16, -c0, mq[4], -c1, mq[5]); expp16(fq + 24, st + 16, c0, mq[6], c1, mq[7]); PINU(fq + 16, 16);
          SCHED_FENCE();
          if (h) {
            mbar_wait(bar_lx, par);
            KV_TILE(pV);
          }
          STG_WAIT();
          PROF(19 + h * 14);
          float o[4][20];
#define O_MMA(hh) { \
            const uint64_t db = make_desc(pV + (hh) * 8192, 16, 1024); \
            ACC_DEF(o[(hh) * 2], 20); ACC_DEF(o[(hh) * 2 + 1], 20); \
            wgmma_fence(); \
            wgmma_n40_rs<0>(o[(hh) * 2], fq + (hh) * 16, db + 256); wgmma_n40_rs<0>(o[(hh) * 2 + 1], fq + (hh) * 16 + 8, db); \
            wgmma_n40_rs<1>(o[(hh) * 2], fq + (hh) * 16 + 4, db + 384); wgmma_n40_rs<1>(o[(hh) * 2 + 1], fq + (hh) * 16 + 12, db + 128); \
            wgmma_commit(); }
          O_MMA(0);
          PMASKS(true, O_BIT(l));
#pragma unroll
          for (int hh = 0; hh < 2; hh++) {
            if (hh && !OW) O_MMA(1);
            wgmma_wait<0>();
            ACC_FENCE(o[hh * 2], 20); ACC_FENCE(o[hh * 2 + 1], 20);
            if (!hh && OW) { O_MMA(1); SCHED_FENCE(); }
            const float* x = o[hh * 2];
            const float* y = o[hh * 2 + 1];
            const float rx0 = rcp_fast(x[17]), ry0 = rcp_fast(y[17]), rx1 = rcp_fast(x[19]), ry1 = rcp_fast(y[19]);
            const float i0 = rcp_fast(fmaf(x[16], rx0, y[16] * ry0) + 1e-6f), i1 = rcp_fast(fmaf(x[18], rx1, y[18] * ry1) + 1e-6f);
            const float ax0 = rx0 * i0, ay0 = ry0 * i0, ax1 = rx1 * i1, ay1 = ry1 * i1;
#pragma unroll
            for (int dp = 0; dp < 2; dp++)
              stsm_x4(pO + srowoff + ((hh * 64 + dp * 32 + lhi) ^ lsw),
                      PBIT0(pack_bf16(fmaf(x[dp * 8], ax0, y[dp * 8] * ay0), fmaf(x[dp * 8 + 1], ax0, y[dp * 8 + 1] * ay0))),
                      PBIT0(pack_bf16(fmaf(x[dp * 8 + 2], ax1, y[dp * 8 + 2] * ay1), fmaf(x[dp * 8 + 3], ax1, y[dp * 8 + 3] * ay1))),
                      PBIT1(pack_bf16(fmaf(x[dp * 8 + 4], ax0, y[dp * 8 + 4] * ay0), fmaf(x[dp * 8 + 5], ax0, y[dp * 8 + 5] * ay0))),
                      PBIT1(pack_bf16(fmaf(x[dp * 8 + 6], ax1, y[dp * 8 + 6] * ay1), fmaf(x[dp * 8 + 7], ax1, y[dp * 8 + 7] * ay1))));
          }
          PUBLISH_O();
          PROF(20 + h * 14);
          if (h) break;
#pragma unroll
          for (int i = 0; i < 32; i++) st[i] = S1[32 + i];
          PIN(st, 32);
          LOAD_X();
          bar_wg(wg);
          WSTEP();
          SCHED_FENCE();
          extrema(mq, st, c0, c1);
          PIN(mq, 8);
          PROF(31);
        }
      }
      __syncwarp();
      if (elect_one()) mbar_arrive_local(bar_epi);
      bar_wg(wg);
#pragma unroll 1
      while (ub < bar_full + 384) {
        WSTEP();
        if (ub == bar_full + 8 * 41) { asm volatile("cp.async.bulk.wait_group.read 0;" ::: "memory"); PROF(35); }
        if (ub == bar_full + 8 * 42) PROF(36);
      }
      wgmma_wait<0>();
      ACC_FENCE(S1, 64);
      REL(bar_done + 47 * 8);
      PROF(37);
      {
        LANE_CONSTS();
        X_OUT(0, l < NLAYERS - 1);
        WARP_STORE(l < NLAYERS - 1 ? &tm_os : &tm_xo, pK, jj * 128, mm * 128 + (l < NLAYERS - 1 ? S_LEN : 0));
        if (l == NLAYERS - 1) {
          X_OUT(1, false);
          WARP_STORE(&tm_xo, pV, jj * 128 + 64, mm * 128);
          asm volatile("cp.async.bulk.wait_group 0;" ::: "memory");
        }
      }
#pragma unroll
      for (int i = 32; i < 64; i++) { uint32_t c; asm volatile("mov.b32 %0, %1;" : "=r"(c) : "f"(S1[i])); S1[i] = __uint_as_float(c); }
      PROF(38);
    }
    const int tid = threadIdx.x;
    if (tid == 0) {
      unsigned old = atomicAdd(&g_flags.done.v, 1);
      if (old == ep1 * NMAIN - 1) {
        asm volatile("st.relaxed.gpu.global.u32 [%0], %1;" :: "l"(&g_flags.epoch.v), "r"(ep1) : "memory");
      }
    }
    __syncwarp();
    cluster_sync();
  }
}

typedef CUresult (*PFN_encode)(CUtensorMap*, CUtensorMapDataType, cuuint32_t, void*, const cuuint64_t*, const cuuint64_t*,
                               const cuuint32_t*, const cuuint32_t*, CUtensorMapInterleave, CUtensorMapSwizzle,
                               CUtensorMapL2promotion, CUtensorMapFloatOOBfill);

CUtensorMap make_map(PFN_encode enc, const void* ptr, uint64_t inner, uint64_t outer, uint32_t box_inner, uint32_t box_outer,
                     CUtensorMapSwizzle swz = CU_TENSOR_MAP_SWIZZLE_128B) {
  CUtensorMap m;
  cuuint64_t dims[2] = {inner, outer};
  cuuint64_t strides[1] = {inner * 2};
  cuuint32_t box[2] = {box_inner, box_outer};
  cuuint32_t es[2] = {1, 1};
  enc(&m, CU_TENSOR_MAP_DATA_TYPE_BFLOAT16, 2, const_cast<void*>(ptr), dims, strides, box, es, CU_TENSOR_MAP_INTERLEAVE_NONE,
      swz, CU_TENSOR_MAP_L2_PROMOTION_L2_256B, CU_TENSOR_MAP_FLOAT_OOB_FILL_NONE);
  return m;
}

}

extern "C" void kernel_launch(void* const* d_in, const int* in_sizes, int n_in, void* d_out, int out_size) {
  (void)in_sizes; (void)n_in; (void)out_size;
  static PFN_encode enc = nullptr;
  if (!enc) {
    void* fn = nullptr;
    cudaDriverEntryPointQueryResult qr;
    cudaGetDriverEntryPoint("cuTensorMapEncodeTiled", &fn, cudaEnableDefault, &qr);
    enc = (PFN_encode)fn;
    cudaFuncSetAttribute(mega_kernel, cudaFuncAttributeMaxDynamicSharedMemorySize, SMEM_BYTES);
  }
  Params prm;
  prm.x0 = (const __nv_bfloat16*)d_in[0];
  prm.wA_qkv = (const __nv_bfloat16*)d_in[1];
  prm.wA_o = (const __nv_bfloat16*)d_in[2];
  prm.wB_qkv = (const __nv_bfloat16*)d_in[4];
  prm.wB_phi = (const __nv_bfloat16*)d_in[5];
  prm.wB_o = (const __nv_bfloat16*)d_in[6];
  prm.out = (__nv_bfloat16*)d_out;
  void *obuf = nullptr, *wf = nullptr;
  cudaGetSymbolAddress(&obuf, g_obuf);
  cudaGetSymbolAddress(&wf, g_wfold);
  CUtensorMap tm_x0 = make_map(enc, d_in[0], D_MODEL, S_LEN, 64, 128);
  CUtensorMap tm_xo = make_map(enc, d_out, D_MODEL, S_LEN, 64, 16);
  CUtensorMap tm_os = make_map(enc, obuf, D_MODEL, 2 * S_LEN, 64, 16);
  CUtensorMap tm_o = make_map(enc, obuf, D_MODEL, 2 * S_LEN, 64, 128);
  CUtensorMap tm_wf = make_map(enc, wf, 2048, D_MODEL, 64, 32);
  CUtensorMap tm_wqA = make_map(enc, d_in[1], 3 * D_MODEL, D_MODEL, 64, 32);
  CUtensorMap tm_wqB = make_map(enc, prm.wB_qkv, 3 * D_MODEL, D_MODEL, 64, 32);
  CUtensorMap tm_woA = make_map(enc, prm.wA_o, D_MODEL, D_MODEL, 64, 64);
  CUtensorMap tm_woB = make_map(enc, prm.wB_o, D_MODEL, D_MODEL, 64, 64);
  CUtensorMap tm_phi = make_map(enc, prm.wB_phi, 32, 1024, 32, 128, CU_TENSOR_MAP_SWIZZLE_64B);
  mega_kernel<<<NMAIN + NAUX, 384, SMEM_BYTES>>>(tm_x0, tm_xo, tm_os, tm_o, tm_wf, tm_wqA, tm_wqB, tm_woA, tm_woB, tm_phi, prm);
}
```

```cpp
#include <cuda_runtime.h>
#include <cuda.h>
#include <cuda_bf16.h>
#include <stdint.h>

#define NLAYERS 4

#define STAG1 300
#define HPUMP1 2
#define HPUMP2 2
#define ASKEW 2
#define FPUMP 2
#define PFGAP 100
#define POLLW 4
#define POLL0 0
#define POLLGAP 120
#define OW 1
#define KT0 1
#define NPOLL 4
#define FILL 40
#define BMASK 0x1F
#define ASITE 1
namespace {

constexpr int S_LEN = 2048, D_MODEL = 1024;
constexpr int NAUX = 4, NMAIN = 128;
constexpr int SLOT = 16384;
constexpr int QST = 24576;
constexpr int OFF_RA = 6 * SLOT, OFF_S = 10 * SLOT;
constexpr int OFF_HALO = 13 * SLOT, OFF_LNB = OFF_HALO  , OFF_ONES = OFF_HALO + 3072;
constexpr int OFF_ST = OFF_HALO + 7168  , OFF_PHI = OFF_HALO + 8192;
constexpr int OFF_BAR = 14 * SLOT;
constexpr int OFF_LNA = OFF_BAR + 1024;
constexpr int SMEM_BYTES = OFF_LNA + 2048;
#define WO_ASLOT(par) ((par) ? 0x9876CAB39876CA98ull : 0x98C76BA398C7698Cull)
constexpr unsigned long long WO_BSLOT = 0x5432105421054210ull;
__device__ __forceinline__ int kslice(int j, int i) { return i < 2 ? 2 * j + i : (i < 9 ? 2 * ((j + i - 1) & 7) : 2 * ((j + i) & 7) + 1); }
__device__ __forceinline__ int wslice(int j, int s) { return 2 * ((j + s) & 7) + (s >> 3); }
constexpr int KVH = 5 * 128 * 4;

struct __align__(128) Flag { unsigned v; unsigned pad[31]; };
struct Flags {
  Flag xready[4][16];
  Flag kvready[4][8][16];
  Flag wfready[8];
  Flag done;
  Flag epoch;
};

__device__ Flags g_flags;
__device__ __nv_bfloat16 g_obuf[2 * S_LEN * D_MODEL];
#define O_BIT(l) ((epoch * NLAYERS + (l) + 1) & 1u)
#define X_BIT(l) ((epoch * (NLAYERS - 1) + (l) + 1) & 1u)
__device__ __nv_bfloat16 g_wfold[D_MODEL * 2048];
__device__ uint4 g_halo[16 * 8 * 512];
__device__ float g_kv[2][32 * KVH];
__device__ __align__(128) uint2 g_colsum[2][1536][2];
__device__ __align__(128) uint2 g_stats[S_LEN * 8];
#define STAT_TAG(l) ((ep1 * NLAYERS + (l) + 1) & 3u)

#define RETRY_COUNT()
#define PROFL 1
#define PROFW 0
#define KVFLAG 1
#define PROFT(i) do {} while (0)
#define PROF(i) do {} while (0)

__device__ __forceinline__ uint32_t smem_u32(const void* p) { return (uint32_t)__cvta_generic_to_shared(p); }
__device__ __forceinline__ bool elect_one() {
  uint32_t p;
  asm volatile("{\n.reg .pred p;\nelect.sync _|p, 0xffffffff;\nselp.u32 %0, 1, 0, p;\n}\n" : "=r"(p));
  return p != 0;
}
__device__ __forceinline__ void mbar_init(uint32_t bar, uint32_t cnt) {
  asm volatile("mbarrier.init.shared::cta.b64 [%0], %1;" :: "r"(bar), "r"(cnt));
}
__device__ __forceinline__ void mbar_expect_tx(uint32_t bar, uint32_t bytes) {
  asm volatile("mbarrier.arrive.expect_tx.shared::cta.b64 _, [%0], %1;" :: "r"(bar), "r"(bytes) : "memory");
}
#define mbar_wait(bar, parity) \
  asm volatile("{\n.reg .pred p, q;\nW_%=:\nmbarrier.try_wait.parity.shared::cta.b64 p, [%1], %2;\nadd.s32 %0, %0, -1;\n" \
               "setp.gt.and.s32 q, %0, 0, !p;\n@q bra.uni W_%=;\n}\n" : "+r"(budget) : "r"((uint32_t)(bar)), "r"((uint32_t)(parity)) : "memory")
#define mbar_wait_sl(bar, parity) \
  asm volatile("{\n.reg .pred p, q;\nW_%=:\nmbarrier.try_wait.parity.shared::cta.b64 p, [%1], %2, 20000;\nadd.s32 %0, %0, -64;\n" \
               "setp.gt.and.s32 q, %0, 0, !p;\n@q bra.uni W_%=;\n}\n" : "+r"(budget) : "r"((uint32_t)(bar)), "r"((uint32_t)(parity)) : "memory")
__device__ __forceinline__ void mbar_arrive_local(uint32_t bar) {
  asm volatile("mbarrier.arrive.shared::cta.b64 _, [%0];" :: "r"(bar) : "memory");
}
__device__ __forceinline__ void tma_load_2d(uint32_t dst, const CUtensorMap* tm, uint32_t bar, int c0, int c1) {
  asm volatile("cp.async.bulk.tensor.2d.shared::cluster.global.mbarrier::complete_tx::bytes [%0], [%1, {%3, %4}], [%2];"
               :: "r"(dst), "l"(tm), "r"(bar), "r"(c0), "r"(c1) : "memory");
}
__device__ __forceinline__ void tma_load_2d_mc(uint32_t dst, const CUtensorMap* tm, uint32_t bar, int c0, int c1) {
  asm volatile("cp.async.bulk.tensor.2d.shared::cluster.global.mbarrier::complete_tx::bytes.multicast::cluster [%0], [%1, {%3, %4}], [%2], %5;"
               :: "r"(dst), "l"(tm), "r"(bar), "r"(c0), "r"(c1), "h"((uint16_t)3) : "memory");
}
__device__ __forceinline__ void tma_store_2d(const CUtensorMap* tm, uint32_t src, int c0, int c1) {
  asm volatile("cp.async.bulk.tensor.2d.global.shared::cta.bulk_group [%0, {%2, %3}], [%1];"
               :: "l"(tm), "r"(src), "r"(c0), "r"(c1) : "memory");
}
__device__ __forceinline__ void bulk_commit_wait() {
  asm volatile("cp.async.bulk.commit_group;\ncp.async.bulk.wait_group 0;" ::: "memory");
}
__device__ __forceinline__ void prefetch_tmap(const CUtensorMap* tm) {
  asm volatile("prefetch.tensormap [%0];" :: "l"(tm) : "memory");
}
__device__ __forceinline__ void fence_proxy_async_global() { asm volatile("fence.proxy.async.global;" ::: "memory"); }
__device__ __forceinline__ void fence_proxy_async_smem() { asm volatile("fence.proxy.async.shared::cta;" ::: "memory"); }
__device__ __forceinline__ unsigned ld_relaxed(const unsigned* p) {
  unsigned v;
  asm volatile("ld.relaxed.gpu.global.u32 %0, [%1];" : "=r"(v) : "l"(p) : "memory");
  return v;
}
__device__ __forceinline__ void fence_acquire() { asm volatile("fence.acquire.gpu;" ::: "memory"); }
__device__ __forceinline__ void wait_flag(const unsigned* p, unsigned target) {
  int it = 0;
  while ((int)(ld_relaxed(p) - target) < 0 && ++it < (1 << 20)) {}
  fence_acquire();
}
__device__ __forceinline__ void signal_release(unsigned* p) {
  asm volatile("red.release.gpu.global.add.u32 [%0], 1;" :: "l"(p) : "memory");
}
template <int ID, int N> __device__ __forceinline__ void bar_arrive() { asm volatile("bar.arrive %0, %1;" :: "n"(ID), "n"(N) : "memory"); }
template <int ID, int N> __device__ __forceinline__ void bar_sync() { asm volatile("bar.sync %0, %1;" :: "n"(ID), "n"(N) : "memory"); }
__device__ __forceinline__ void bar_wg(int wg) { asm volatile("bar.sync %0, 128;" :: "r"(2 + wg) : "memory"); }
__device__ __forceinline__ void cluster_sync() {
  asm volatile("barrier.cluster.arrive.relaxed.aligned;\nbarrier.cluster.wait.aligned;" ::: "memory");
}
__device__ __forceinline__ void cluster_wait() { asm volatile("barrier.cluster.wait.acquire.aligned;" ::: "memory"); }
enum { BAR_KV = 4  , BAR_O = 7  , BAR_WF = 12  , BAR_SKEW = 13 };

__device__ __forceinline__ void wgmma_fence() { asm volatile("wgmma.fence.sync.aligned;" ::: "memory"); }
__device__ __forceinline__ void wgmma_commit() { asm volatile("wgmma.commit_group.sync.aligned;" ::: "memory"); }
template <int N> __device__ __forceinline__ void wgmma_wait() { asm volatile("wgmma.wait_group.sync.aligned %0;" :: "n"(N) : "memory"); }

template <int scale_d, int tnsp_b = 1> __device__ __forceinline__ void wgmma_n192(float* d, uint64_t descA, uint64_t descB) {
  asm volatile("{\n.reg .pred p;\nsetp.ne.b32 p, %98, 0;\n"
               "wgmma.mma_async.sync.aligned.m64n192k16.f32.bf16.bf16 {%0,%1,%2,%3,%4,%5,%6,%7,%8,%9,%10,%11,%12,%13,%14,%15,%16,%17,%18,%19,%20,%21,%22,%23,%24,%25,%26,%27,%28,%29,%30,%31,%32,%33,%34,%35,%36,%37,%38,%39,%40,%41,%42,%43,%44,%45,%46,%47,%48,%49,%50,%51,%52,%53,%54,%55,%56,%57,%58,%59,%60,%61,%62,%63,%64,%65,%66,%67,%68,%69,%70,%71,%72,%73,%74,%75,%76,%77,%78,%79,%80,%81,%82,%83,%84,%85,%86,%87,%88,%89,%90,%91,%92,%93,%94,%95}, %96, %97, p, 1, 1, 0, %99;\n}\n"
               : "+f"(d[0]), "+f"(d[1]), "+f"(d[2]), "+f"(d[3]), "+f"(d[4]), "+f"(d[5]), "+f"(d[6]), "+f"(d[7]), "+f"(d[8]), "+f"(d[9]), "+f"(d[10]), "+f"(d[11]), "+f"(d[12]), "+f"(d[13]), "+f"(d[14]), "+f"(d[15]), "+f"(d[16]), "+f"(d[17]), "+f"(d[18]), "+f"(d[19]), "+f"(d[20]), "+f"(d[21]), "+f"(d[22]), "+f"(d[23]), "+f"(d[24]), "+f"(d[25]), "+f"(d[26]), "+f"(d[27]), "+f"(d[28]), "+f"(d[29]), "+f"(d[30]), "+f"(d[31]), "+f"(d[32]), "+f"(d[33]), "+f"(d[34]), "+f"(d[35]), "+f"(d[36]), "+f"(d[37]), "+f"(d[38]), "+f"(d[39]), "+f"(d[40]), "+f"(d[41]), "+f"(d[42]), "+f"(d[43]), "+f"(d[44]), "+f"(d[45]), "+f"(d[46]), "+f"(d[47]), "+f"(d[48]), "+f"(d[49]), "+f"(d[50]), "+f"(d[51]), "+f"(d[52]), "+f"(d[53]), "+f"(d[54]), "+f"(d[55]), "+f"(d[56]), "+f"(d[57]), "+f"(d[58]), "+f"(d[59]), "+f"(d[60]), "+f"(d[61]), "+f"(d[62]), "+f"(d[63]), "+f"(d[64]), "+f"(d[65]), "+f"(d[66]), "+f"(d[67]), "+f"(d[68]), "+f"(d[69]), "+f"(d[70]), "+f"(d[71]), "+f"(d[72]), "+f"(d[73]), "+f"(d[74]), "+f"(d[75]), "+f"(d[76]), "+f"(d[77]), "+f"(d[78]), "+f"(d[79]), "+f"(d[80]), "+f"(d[81]), "+f"(d[82]), "+f"(d[83]), "+f"(d[84]), "+f"(d[85]), "+f"(d[86]), "+f"(d[87]), "+f"(d[88]), "+f"(d[89]), "+f"(d[90]), "+f"(d[91]), "+f"(d[92]), "+f"(d[93]), "+f"(d[94]), "+f"(d[95])
               : "l"(descA), "l"(descB), "n"(scale_d), "n"(tnsp_b));
}
template <int scale_d> __device__ __forceinline__ void wgmma4_n192(float* d, uint32_t da, uint32_t db) {
#define R_ "{%0,%1,%2,%3,%4,%5,%6,%7,%8,%9,%10,%11,%12,%13,%14,%15,%16,%17,%18,%19,%20,%21,%22,%23,%24,%25,%26,%27,%28,%29,%30,%31,%32,%33,%34,%35,%36,%37,%38,%39,%40,%41,%42,%43,%44,%45,%46,%47,%48,%49,%50,%51,%52,%53,%54,%55,%56,%57,%58,%59,%60,%61,%62,%63,%64,%65,%66,%67,%68,%69,%70,%71,%72,%73,%74,%75,%76,%77,%78,%79,%80,%81,%82,%83,%84,%85,%86,%87,%88,%89,%90,%91,%92,%93,%94,%95}"
  asm volatile("{\n.reg .pred p, q;\n.reg .b64 a, b;\nsetp.ne.b32 p, %98, 0;\nsetp.eq.b32 q, 0, 0;\nmov.b64 a, {%96, 0x40000040};\nmov.b64 b, {%97, 0x40000040};\n"
               "wgmma.mma_async.sync.aligned.m64n192k16.f32.bf16.bf16 " R_ ", a, b, p, 1, 1, 0, 1;\nadd.s64 a, a, 2;\nadd.s64 b, b, 128;\n"
               "wgmma.mma_async.sync.aligned.m64n192k16.f32.bf16.bf16 " R_ ", a, b, q, 1, 1, 0, 1;\nadd.s64 a, a, 2;\nadd.s64 b, b, 128;\n"
               "wgmma.mma_async.sync.aligned.m64n192k16.f32.bf16.bf16 " R_ ", a, b, q, 1, 1, 0, 1;\nadd.s64 a, a, 2;\nadd.s64 b, b, 128;\n"
               "wgmma.mma_async.sync.aligned.m64n192k16.f32.bf16.bf16 " R_ ", a, b, q, 1, 1, 0, 1;\n}\n"
               : "+f"(d[0]), "+f"(d[1]), "+f"(d[2]), "+f"(d[3]), "+f"(d[4]), "+f"(d[5]), "+f"(d[6]), "+f"(d[7]), "+f"(d[8]), "+f"(d[9]), "+f"(d[10]), "+f"(d[11]), "+f"(d[12]), "+f"(d[13]), "+f"(d[14]), "+f"(d[15]), "+f"(d[16]), "+f"(d[17]), "+f"(d[18]), "+f"(d[19]), "+f"(d[20]), "+f"(d[21]), "+f"(d[22]), "+f"(d[23]), "+f"(d[24]), "+f"(d[25]), "+f"(d[26]), "+f"(d[27]), "+f"(d[28]), "+f"(d[29]), "+f"(d[30]), "+f"(d[31]), "+f"(d[32]), "+f"(d[33]), "+f"(d[34]), "+f"(d[35]), "+f"(d[36]), "+f"(d[37]), "+f"(d[38]), "+f"(d[39]), "+f"(d[40]), "+f"(d[41]), "+f"(d[42]), "+f"(d[43]), "+f"(d[44]), "+f"(d[45]), "+f"(d[46]), "+f"(d[47]), "+f"(d[48]), "+f"(d[49]), "+f"(d[50]), "+f"(d[51]), "+f"(d[52]), "+f"(d[53]), "+f"(d[54]), "+f"(d[55]), "+f"(d[56]), "+f"(d[57]), "+f"(d[58]), "+f"(d[59]), "+f"(d[60]), "+f"(d[61]), "+f"(d[62]), "+f"(d[63]), "+f"(d[64]), "+f"(d[65]), "+f"(d[66]), "+f"(d[67]), "+f"(d[68]), "+f"(d[69]), "+f"(d[70]), "+f"(d[71]), "+f"(d[72]), "+f"(d[73]), "+f"(d[74]), "+f"(d[75]), "+f"(d[76]), "+f"(d[77]), "+f"(d[78]), "+f"(d[79]), "+f"(d[80]), "+f"(d[81]), "+f"(d[82]), "+f"(d[83]), "+f"(d[84]), "+f"(d[85]), "+f"(d[86]), "+f"(d[87]), "+f"(d[88]), "+f"(d[89]), "+f"(d[90]), "+f"(d[91]), "+f"(d[92]), "+f"(d[93]), "+f"(d[94]), "+f"(d[95])
               : "r"(da), "r"(db), "n"(scale_d));
#undef R_
}
template <int scale_d> __device__ __forceinline__ void wgmma4_n128(float* d, uint32_t da, uint32_t db) {
#define R_ "{%0,%1,%2,%3,%4,%5,%6,%7,%8,%9,%10,%11,%12,%13,%14,%15,%16,%17,%18,%19,%20,%21,%22,%23,%24,%25,%26,%27,%28,%29,%30,%31,%32,%33,%34,%35,%36,%37,%38,%39,%40,%41,%42,%43,%44,%45,%46,%47,%48,%49,%50,%51,%52,%53,%54,%55,%56,%57,%58,%59,%60,%61,%62,%63}"
  asm volatile("{\n.reg .pred p, q;\n.reg .b64 a, b;\nsetp.ne.b32 p, %66, 0;\nsetp.eq.b32 q, 0, 0;\nmov.b64 a, {%64, 0x40000040};\nmov.b64 b, {%65, 0x40000040};\n"
               "wgmma.mma_async.sync.aligned.m64n128k16.f32.bf16.bf16 " R_ ", a, b, p, 1, 1, 0, 1;\nadd.s64 a, a, 2;\nadd.s64 b, b, 128;\n"
               "wgmma.mma_async.sync.aligned.m64n128k16.f32.bf16.bf16 " R_ ", a, b, q, 1, 1, 0, 1;\nadd.s64 a, a, 2;\nadd.s64 b, b, 128;\n"
               "wgmma.mma_async.sync.aligned.m64n128k16.f32.bf16.bf16 " R_ ", a, b, q, 1, 1, 0, 1;\nadd.s64 a, a, 2;\nadd.s64 b, b, 128;\n"
               "wgmma.mma_async.sync.aligned.m64n128k16.f32.bf16.bf16 " R_ ", a, b, q, 1, 1, 0, 1;\n}\n"
               : "+f"(d[0]), "+f"(d[1]), "+f"(d[2]), "+f"(d[3]), "+f"(d[4]), "+f"(d[5]), "+f"(d[6]), "+f"(d[7]), "+f"(d[8]), "+f"(d[9]), "+f"(d[10]), "+f"(d[11]), "+f"(d[12]), "+f"(d[13]), "+f"(d[14]), "+f"(d[15]), "+f"(d[16]), "+f"(d[17]), "+f"(d[18]), "+f"(d[19]), "+f"(d[20]), "+f"(d[21]), "+f"(d[22]), "+f"(d[23]), "+f"(d[24]), "+f"(d[25]), "+f"(d[26]), "+f"(d[27]), "+f"(d[28]), "+f"(d[29]), "+f"(d[30]), "+f"(d[31]), "+f"(d[32]), "+f"(d[33]), "+f"(d[34]), "+f"(d[35]), "+f"(d[36]), "+f"(d[37]), "+f"(d[38]), "+f"(d[39]), "+f"(d[40]), "+f"(d[41]), "+f"(d[42]), "+f"(d[43]), "+f"(d[44]), "+f"(d[45]), "+f"(d[46]), "+f"(d[47]), "+f"(d[48]), "+f"(d[49]), "+f"(d[50]), "+f"(d[51]), "+f"(d[52]), "+f"(d[53]), "+f"(d[54]), "+f"(d[55]), "+f"(d[56]), "+f"(d[57]), "+f"(d[58]), "+f"(d[59]), "+f"(d[60]), "+f"(d[61]), "+f"(d[62]), "+f"(d[63])
               : "r"(da), "r"(db), "n"(scale_d));
#undef R_
}
template <int scale_d> __device__ __forceinline__ void wgmma_n32(float* d, uint64_t descA, uint64_t descB) {
  asm volatile("{\n.reg .pred p;\nsetp.ne.b32 p, %18, 0;\n"
               "wgmma.mma_async.sync.aligned.m64n32k16.f32.bf16.bf16 {%0,%1,%2,%3,%4,%5,%6,%7,%8,%9,%10,%11,%12,%13,%14,%15}, %16, %17, p, 1, 1, 0, 1;\n}\n"
               : "+f"(d[0]), "+f"(d[1]), "+f"(d[2]), "+f"(d[3]), "+f"(d[4]), "+f"(d[5]), "+f"(d[6]), "+f"(d[7]), "+f"(d[8]), "+f"(d[9]), "+f"(d[10]), "+f"(d[11]), "+f"(d[12]), "+f"(d[13]), "+f"(d[14]), "+f"(d[15])
               : "l"(descA), "l"(descB), "n"(scale_d));
}
template <int scale_d, int tnsp_a> __device__ __forceinline__ void wgmma_n40(float* d, uint64_t descA, uint64_t descB) {
  asm volatile("{\n.reg .pred p;\nsetp.ne.b32 p, %22, 0;\n"
               "wgmma.mma_async.sync.aligned.m64n40k16.f32.bf16.bf16 {%0,%1,%2,%3,%4,%5,%6,%7,%8,%9,%10,%11,%12,%13,%14,%15,%16,%17,%18,%19}, %20, %21, p, 1, 1, %23, 1;\n}\n"
               : "+f"(d[0]), "+f"(d[1]), "+f"(d[2]), "+f"(d[3]), "+f"(d[4]), "+f"(d[5]), "+f"(d[6]), "+f"(d[7]), "+f"(d[8]), "+f"(d[9]), "+f"(d[10]), "+f"(d[11]), "+f"(d[12]), "+f"(d[13]), "+f"(d[14]), "+f"(d[15]), "+f"(d[16]), "+f"(d[17]), "+f"(d[18]), "+f"(d[19])
               : "l"(descA), "l"(descB), "n"(scale_d), "n"(tnsp_a));
}
template <int scale_d> __device__ __forceinline__ void wgmma_n40_rs(float* d, const uint32_t* a, uint64_t descB) {
  asm volatile("{\n.reg .pred p;\nsetp.ne.b32 p, %25, 0;\n"
               "wgmma.mma_async.sync.aligned.m64n40k16.f32.bf16.bf16 {%0,%1,%2,%3,%4,%5,%6,%7,%8,%9,%10,%11,%12,%13,%14,%15,%16,%17,%18,%19}, {%20,%21,%22,%23}, %24, p, 1, 1, 1;\n}\n"
               : "+f"(d[0]), "+f"(d[1]), "+f"(d[2]), "+f"(d[3]), "+f"(d[4]), "+f"(d[5]), "+f"(d[6]), "+f"(d[7]), "+f"(d[8]), "+f"(d[9]), "+f"(d[10]), "+f"(d[11]), "+f"(d[12]), "+f"(d[13]), "+f"(d[14]), "+f"(d[15]), "+f"(d[16]), "+f"(d[17]), "+f"(d[18]), "+f"(d[19])
               : "r"(a[0]), "r"(a[1]), "r"(a[2]), "r"(a[3]), "l"(descB), "n"(scale_d));
}
__device__ __forceinline__ uint64_t make_desc(uint32_t addr, uint32_t lbo_bytes, uint32_t sbo_bytes) {
  return (uint64_t)((addr & 0x3FFFF) >> 4) | ((uint64_t)(lbo_bytes >> 4) << 16) | ((uint64_t)(sbo_bytes >> 4) << 32) | (1ull << 62);
}

__device__ __forceinline__ void ldsm_x4(uint32_t addr, uint32_t& r0, uint32_t& r1, uint32_t& r2, uint32_t& r3) {
  asm volatile("ldmatrix.sync.aligned.m8n8.x4.shared.b16 {%0,%1,%2,%3}, [%4];" : "=r"(r0), "=r"(r1), "=r"(r2), "=r"(r3) : "r"(addr) : "memory");
}
__device__ __forceinline__ void ldsm_x4_t(uint32_t addr, uint32_t& r0, uint32_t& r1, uint32_t& r2, uint32_t& r3) {
  asm volatile("ldmatrix.sync.aligned.m8n8.x4.trans.shared.b16 {%0,%1,%2,%3}, [%4];" : "=r"(r0), "=r"(r1), "=r"(r2), "=r"(r3) : "r"(addr) : "memory");
}
__device__ __forceinline__ void stsm_x4(uint32_t addr, uint32_t r0, uint32_t r1, uint32_t r2, uint32_t r3) {
  asm volatile("stmatrix.sync.aligned.m8n8.x4.shared.b16 [%0], {%1,%2,%3,%4};" :: "r"(addr), "r"(r0), "r"(r1), "r"(r2), "r"(r3) : "memory");
}
__device__ __forceinline__ void sts128(uint32_t addr, uint32_t a, uint32_t b, uint32_t c, uint32_t d) {
  asm volatile("st.shared.v4.u32 [%0], {%1,%2,%3,%4};" :: "r"(addr), "r"(a), "r"(b), "r"(c), "r"(d) : "memory");
}
__device__ __forceinline__ float lds32f(uint32_t addr) {
  float v;
  asm volatile("ld.shared.f32 %0, [%1];" : "=f"(v) : "r"(addr) : "memory");
  return v;
}
__device__ __forceinline__ void sts32f(uint32_t addr, float a) {
  asm volatile("st.shared.f32 [%0], %1;" :: "r"(addr), "f"(a) : "memory");
}
__device__ __forceinline__ void mma_bf16(float (&c)[4], uint32_t a0, uint32_t a1, uint32_t a2, uint32_t a3, uint32_t b0, uint32_t b1) {
  asm volatile("mma.sync.aligned.m16n8k16.row.col.f32.bf16.bf16.f32 {%0,%1,%2,%3}, {%4,%5,%6,%7}, {%8,%9}, {%0,%1,%2,%3};"
               : "+f"(c[0]), "+f"(c[1]), "+f"(c[2]), "+f"(c[3]) : "r"(a0), "r"(a1), "r"(a2), "r"(a3), "r"(b0), "r"(b1));
}
__device__ __forceinline__ uint32_t pack_bf16(float lo, float hi) {
  uint32_t r;
  asm("cvt.rn.bf16x2.f32 %0, %1, %2;" : "=r"(r) : "f"(hi), "f"(lo));
  return r;
}
__device__ __forceinline__ float bf_lo(uint32_t v) { return __uint_as_float(v << 16); }
__device__ __forceinline__ float bf_hi(uint32_t v) { return __uint_as_float(v & 0xFFFF0000u); }
__device__ __forceinline__ void split3(float x, uint32_t& h, uint32_t& m, uint32_t& l) {
  h = pack_bf16(x, 0.f); x -= bf_lo(h);
  m = pack_bf16(x, 0.f); x -= bf_lo(m);
  l = pack_bf16(x, 0.f);
}
__device__ __forceinline__ float ex2(float x) { float r; asm("ex2.approx.ftz.f32 %0, %1;" : "=f"(r) : "f"(x)); return r; }
__device__ __forceinline__ float rcp_fast(float x) { float r; asm("rcp.approx.ftz.f32 %0, %1;" : "=f"(r) : "f"(x)); return r; }
__device__ __forceinline__ void red_v4(float* p, float a, float b, float c, float d) {
  asm volatile("red.global.add.v4.f32 [%0], {%1, %2, %3, %4};" :: "l"(p), "f"(a), "f"(b), "f"(c), "f"(d) : "memory");
}
__device__ __forceinline__ uint4 ld_ll(const uint4* p) {
  uint4 v;
  asm volatile("{\n.reg .b64 a, b;\nld.relaxed.gpu.global.v2.b64 {a, b}, [%4];\nmov.b64 {%0, %1}, a;\nmov.b64 {%2, %3}, b;\n}\n"
               : "=r"(v.x), "=r"(v.y), "=r"(v.z), "=r"(v.w) : "l"(p) : "memory");
  return v;
}
__device__ __forceinline__ void st_b64(uint2* p, uint32_t a, uint32_t b) {
  asm volatile("{\n.reg .b64 v;\nmov.b64 v, {%1, %2};\nst.relaxed.gpu.global.b64 [%0], v;\n}\n" :: "l"(p), "r"(a), "r"(b) : "memory");
}
__device__ __forceinline__ void st_b128(uint4* p, uint32_t a, uint32_t b, uint32_t c, uint32_t d) {
  asm volatile("{\n.reg .b128 v;\nmov.b128 v, {%1, %2, %3, %4};\nst.relaxed.gpu.global.b128 [%0], v;\n}\n" :: "l"(p), "r"(a), "r"(b), "r"(c), "r"(d) : "memory");
}
__device__ __forceinline__ uint4 ld_b128(const uint4* p) {
  uint4 v;
  asm volatile("{\n.reg .b128 v;\nld.relaxed.gpu.global.b128 v, [%4];\nmov.b128 {%0, %1, %2, %3}, v;\n}\n" : "=r"(v.x), "=r"(v.y), "=r"(v.z), "=r"(v.w) : "l"(p) : "memory");
  return v;
}

constexpr float LOG2E = 1.4426950408889634f;

struct Params {
  const __nv_bfloat16* x0;
  const __nv_bfloat16* wA_qkv;
  const __nv_bfloat16* wA_o;
  const __nv_bfloat16* wB_qkv;
  const __nv_bfloat16* wB_phi;
  const __nv_bfloat16* wB_o;
  __nv_bfloat16* out;
};

#define ACC_DEF(d, n) _Pragma("unroll") for (int i_ = 0; i_ < (n); i_++) asm volatile("" : "=f"(d[i_]))
#define ACC_FENCE(d, n) _Pragma("unroll") for (int i_ = 0; i_ < (n); i_++) asm volatile("" : "+f"(d[i_]) :: "memory")
#define PIN(a, n) _Pragma("unroll") for (int i_ = 0; i_ < (n); i_++) asm volatile("" : "+f"((a)[i_]))
#define PINU(a, n) _Pragma("unroll") for (int i_ = 0; i_ < (n); i_++) asm volatile("" : "+r"((a)[i_]))

#define STAGE64(acc, off, p0, KIND, SEND) { \
    uint32_t w_[4][4]; \
    _Pragma("unroll") for (int j_ = 0; j_ < 4; j_++) { \
      const int o_ = (off) + j_ * 8; \
      w_[j_][0] = pack_bf16(rs0 * acc[o_ + 0], rs0 * acc[o_ + 1]); \
      w_[j_][1] = pack_bf16(rs1 * acc[o_ + 2], rs1 * acc[o_ + 3]); \
      w_[j_][2] = pack_bf16(rs0 * acc[o_ + 4], rs0 * acc[o_ + 5]); \
      w_[j_][3] = pack_bf16(rs1 * acc[o_ + 6], rs1 * acc[o_ + 7]); \
    } \
    if ((SEND) && hsend) { \
      _Pragma("unroll") for (int j_ = 0; j_ < 4; j_++) { \
        w_[j_][0] = (w_[j_][0] & ~1u) | hbit; \
        st_b128(hbase + lane + ((KIND) * 4 + j_) * 32, w_[j_][0], w_[j_][1], w_[j_][2], w_[j_][3]); \
      } \
    } \
    _Pragma("unroll") for (int j_ = 0; j_ < 4; j_++) \
      stsm_x4((KIND) ? (p0) + (j_ >> 1) * 8192 + (srowoff >> 1) + ((((uint32_t)(j_ & 1) << 5) + lhi) ^ lsw2) \
                     : (p0) + srowoff + ((((uint32_t)j_ << 5) + lhi) ^ lsw), \
              w_[j_][0], w_[j_][1], w_[j_][2], w_[j_][3]); \
  }
#define RW(j) (((j) >> 1) * 4 + ((j) & 1))
__device__ __forceinline__ float rmax16(const float* p) {
  float m[4];
#pragma unroll
  for (int j = 0; j < 4; j++) m[j] = fmaxf(fmaxf(p[RW(j)], p[RW(j + 4)]), fmaxf(p[RW(j + 8)], p[RW(j + 12)]));
  const float r = fmaxf(fmaxf(m[0], m[1]), fmaxf(m[2], m[3]));
  return fmaxf(r, __shfl_xor_sync(0xffffffffu, r, 1));
}
__device__ __forceinline__ float rmin16(const float* p) {
  float m[4];
#pragma unroll
  for (int j = 0; j < 4; j++) m[j] = fminf(fminf(p[RW(j)], p[RW(j + 4)]), fminf(p[RW(j + 8)], p[RW(j + 12)]));
  const float r = fminf(fminf(m[0], m[1]), fminf(m[2], m[3]));
  return fminf(r, __shfl_xor_sync(0xffffffffu, r, 1));
}
__device__ __forceinline__ float exps16(float* o, const float* p, float c, float b) {
  float s[4];
#pragma unroll
  for (int j = 0; j < 16; j++) { o[j] = ex2(fmaf(p[RW(j)], c, b)); if (j < 4) s[j] = o[j]; else s[j & 3] += o[j]; }
  return (s[0] + s[1]) + (s[2] + s[3]);
}
__device__ __forceinline__ void store16(const float* e, float sum, uint32_t dst, uint32_t dsw, int c0) {
  const float inv = rcp_fast(sum + __shfl_xor_sync(0xffffffffu, sum, 1));
#pragma unroll
  for (int j = 0; j < 2; j++)
    sts128(dst + (((c0 + j) << 4) ^ dsw), pack_bf16(e[j * 8] * inv, e[j * 8 + 1] * inv), pack_bf16(e[j * 8 + 2] * inv, e[j * 8 + 3] * inv),
           pack_bf16(e[j * 8 + 4] * inv, e[j * 8 + 5] * inv), pack_bf16(e[j * 8 + 6] * inv, e[j * 8 + 7] * inv));
}
__device__ __forceinline__ void expp16(uint32_t* o, const float* p, float c0, float b0, float c1, float b1) {
#pragma unroll
  for (int j = 0; j < 8; j++) {
    const float c = (j & 1) ? c1 : c0, b = (j & 1) ? b1 : b0;
    o[j] = pack_bf16(ex2(fmaf(p[2 * j], c, b)), ex2(fmaf(p[2 * j + 1], c, b)));
  }
}
__device__ __forceinline__ void extrema(float* m, const float* p, float c0, float c1) {
#pragma unroll
  for (int i = 0; i < 4; i++) {
    const float* q = p + (i >> 1) * 16 + (i & 1) * 2;
    m[(i >> 1) * 4 + (i & 1)] = fminf(fminf(fminf(q[0], q[1]), fminf(q[4], q[5])), fminf(fminf(q[8], q[9]), fminf(q[12], q[13])));
    m[(i >> 1) * 4 + (i & 1) + 2] = fmaxf(fmaxf(fmaxf(q[0], q[1]), fmaxf(q[4], q[5])), fmaxf(fmaxf(q[8], q[9]), fmaxf(q[12], q[13])));
  }
#pragma unroll
  for (int o = 1; o <= 2; o <<= 1)
#pragma unroll
    for (int i = 0; i < 8; i++) { const float x = __shfl_xor_sync(0xffffffffu, m[i], o); m[i] = (i & 2) ? fmaxf(m[i], x) : fminf(m[i], x); }
#pragma unroll
  for (int i = 0; i < 8; i++) m[i] *= ((i & 2) ? -1.f : 1.f) * ((i & 1) ? c1 : c0);
}
#define SCHED_FENCE() asm volatile("pmevent 0;" ::: "memory")

__global__ void __cluster_dims__(2, 1, 1) __launch_bounds__(384, 1)
mega_kernel(const __grid_constant__ CUtensorMap tm_x0, const __grid_constant__ CUtensorMap tm_xo, const __grid_constant__ CUtensorMap tm_os,
            const __grid_constant__ CUtensorMap tm_o, const __grid_constant__ CUtensorMap tm_wf,
            const __grid_constant__ CUtensorMap tm_wqA, const __grid_constant__ CUtensorMap tm_wqB,
            const __grid_constant__ CUtensorMap tm_woA, const __grid_constant__ CUtensorMap tm_woB,
            const __grid_constant__ CUtensorMap tm_phi, const Params prm) {
  extern __shared__ __align__(1024) uint8_t smem_raw[];
  const uint32_t sbase = smem_u32(smem_raw);
  const uint32_t bar_full = sbase + OFF_BAR;
  const uint32_t bar_done = bar_full + 384;
  const uint32_t bar_stat = bar_full + 768, bar_stat2 = bar_full + 776, bar_epi = bar_full + 784, bar_phi = bar_full + 936  ;
  const uint32_t bar_xr = bar_full + 800, bar_lx = bar_full + 808, bar_kvf = bar_full + 816  , bar_stg = bar_full + 832;
  const uint32_t bar_chk = bar_full + 848;

  const int warp = __shfl_sync(0xffffffffu, threadIdx.x >> 5, 0), lane = threadIdx.x & 31;
  uint32_t rank;
  asm volatile("mov.u32 %0, %%cluster_ctarank;" : "=r"(rank));
  const int cta = (int)blockIdx.x - NAUX;
  const int cl = cta >> 1;
  const int jj = cl & 7, cc = cl >> 3;
  const int mm = cc * 2 + (int)rank;

#define LOAD_EPOCH() const unsigned epoch = ld_relaxed(&g_flags.epoch.v), ep1 = epoch + 1; (void)epoch
  int budget = 1 << 22;

  if (cta >= 0) {
    {
      const int tx = threadIdx.x;
      const __nv_bfloat16* pf = (tx < 128) ? prm.x0 + (size_t)(mm * 128 + tx) * D_MODEL + jj * 128
                                           : prm.wA_qkv + (size_t)(jj * 128 + (tx & 63)) * 3072 + ((tx - 128) >> 6) * 1024 + jj * 128 + rank * 64;
      if (tx < 320) asm volatile("prefetch.global.L2 [%0];" :: "l"(pf));
      else if (tx == 320) prefetch_tmap(&tm_x0);
      else if (tx == 352) prefetch_tmap(&tm_wqA);
      else if (tx == 383) asm volatile("prefetch.global.L2 [%0];" :: "l"(&g_flags.epoch.v));
    }
    if (elect_one()) {
#pragma unroll
      for (int i = 0; i < 4; i++) {
        const int u = warp * 4 + i;
        mbar_init(bar_full + u * 8, ((u >= 4 && u < 11) || (u > 32 && u != 40)) ? 2 : 1); mbar_init(bar_done + u * 8, 16);
      }
      mbar_init(bar_stat + warp * 16, 0x111111181182ull >> (4 * warp) & 15);
      mbar_init(bar_stat + warp * 16 + 8, 0x111111121811ull >> (4 * warp) & 15);
      mbar_init(bar_chk + 112 + (warp & 7) * 8, 1);
      asm volatile("fence.mbarrier_init.release.cluster;" ::: "memory");
    }
    __syncthreads();
    asm volatile("barrier.cluster.arrive.relaxed.aligned;" ::: "memory");
  }

  if (cta < 0) {
    LOAD_EPOCH();
    const uint32_t buf = sbase + warp * SLOT, bar = sbase + OFF_BAR + warp * 16;
    const uint32_t lsw = (lane & 7) << 4, lhi = (lane >> 4) << 4, lrow = (lane & 15) * 128;
    const bool el = elect_one();
    if (el) {
      mbar_init(bar, 1); mbar_init(bar + 8, 1);
      asm volatile("fence.mbarrier_init.release.cluster;" ::: "memory");
    }
#pragma unroll 1
    for (int rd = 0; rd < (NLAYERS > 1 ? 5 : 2); rd++) {
      if (rd >= 2 && warp >= 8) break;
      const int tk = rd < 2 ? blockIdx.x * 12 + warp : blockIdx.x * 8 + warp;
      const int half = tk & 1;
      const int blk = rd < 2 ? (tk >> 1) * 2 + rd : (4 - rd) * 16 + (tk >> 1);
      const CUtensorMap* tm = rd < 2 ? &tm_wqA : (rd == 2 ? &tm_wqB : &tm_wf);
      const int j0 = (blk & 15) >> 1;
#define AUX_LOAD(n) { const uint32_t d_ = buf + ((n) & 1) * 8192, b_ = bar + ((n) & 1) * 8; const int r_ = kslice(j0, 2 * (n) + half) * 64; \
        mbar_expect_tx(b_, 8192); tma_load_2d(d_, tm, b_, blk * 64, r_); tma_load_2d(d_ + 4096, tm, b_, blk * 64, r_ + 32); }
      if (el) {
        if (rd == 3) { wait_flag(&g_flags.wfready[j0].v, ep1 * 16); fence_proxy_async_global(); }
        AUX_LOAD(0); AUX_LOAD(1);
      }
      __syncwarp();
      float cs[8][4];
#pragma unroll
      for (int i = 0; i < 8; i++) cs[i][0] = cs[i][1] = cs[i][2] = cs[i][3] = 0.f;
#pragma unroll 1
      for (int n = 0; n < 8; n++) {
        const uint32_t tb = buf + (n & 1) * 8192 + lrow;
        mbar_wait(bar + (n & 1) * 8, (n >> 1) & 1);
#pragma unroll
        for (int i = 0; i < 16; i++) {
          uint32_t b0, b1, b2, b3;
          ldsm_x4_t(tb + (i >> 2) * 2048 + (((i & 3) * 32 + lhi) ^ lsw), b0, b1, b2, b3);
          mma_bf16(cs[2 * (i & 3)], 0x3F803F80u, 0x3F803F80u, 0x3F803F80u, 0x3F803F80u, b0, b1);
          mma_bf16(cs[2 * (i & 3) + 1], 0x3F803F80u, 0x3F803F80u, 0x3F803F80u, 0x3F803F80u, b2, b3);
        }
        __syncwarp();
        if (el && n < 6) AUX_LOAD(n + 2);
        __syncwarp();
      }
      if (lane < 4) {
#pragma unroll
        for (int i = 0; i < 8; i++) st_b64(&g_colsum[rd >= 2][blk * 32 + i * 4 + lane][half], __float_as_uint(cs[i][0]), (__float_as_uint(cs[i][1]) & ~3u) | (ep1 & 3));
      }
      __syncwarp();
    }
  } else if (warp >= 8) {
    asm volatile("setmaxnreg.dec.sync.aligned.u32 40;");
    if (warp == 8) {
      const bool el = elect_one();
      cluster_wait();
      if (el) {
#pragma unroll 1
        for (int l = 0; l < NLAYERS; l++) {
          const uint32_t par = l & 1;
          const CUtensorMap* tqk = par ? &tm_wf : &tm_wqA;
          const CUtensorMap* tv = par ? &tm_wqB : &tm_wqA;
          const CUtensorMap* two = par ? &tm_woB : &tm_woA;
          if (l == 1) { LOAD_EPOCH(); wait_flag(&g_flags.wfready[jj].v, ep1 * 16); fence_proxy_async_global(); }
#pragma unroll 1
          for (int u = 0; u < 32; u++) {
            if (u >= 4) mbar_wait_sl(bar_done + (u - 4) * 8, par);
            else if (l) mbar_wait_sl(bar_done + (43 + u + (u >> 1)) * 8, par ^ 1);
            else if (u == 1) __nanosleep(STAG1);
            else if (u == 2) mbar_wait_sl(bar_full, 0);
            const uint32_t fb = bar_full + u * 8;
            const bool res = u < 4 ? (l || u >= 2) : (u < 11 || (u >= 18 && u < 22));
            mbar_expect_tx(fb, res ? QST : QST + SLOT);
            const int row = kslice(jj, u < 4 ? u & 1 : (u < 18 ? u - 2 : (u < 22 ? u - 6 : u - 20))) * 64 + (int)rank * 32;
            const int ps = u < 4 ? u >> 1 : (u >= 18), col = jj * 128 + ps * 64;
            const int c0 = par ? jj * 128 + (ps ? 0 : 1024) : col;
            const uint32_t dst = sbase + (u & 3) * QST + rank * 4096;
            tma_load_2d_mc(dst, tqk, fb, c0, row);
            tma_load_2d_mc(dst + 8192, tqk, fb, c0 + (par ? 64 : 1024), row);
            tma_load_2d_mc(dst + 16384, tv, fb, col + 2048, row);
            if (l == 0 && u < 4) PROFT(473 + u);
          }
#pragma unroll 1
          for (int s = 0; s < 16; s++) {
            if (s < 5) { if (s != 2 && s != 4) mbar_wait_sl(bar_done + (28 + s) * 8, par); }
            else if (s != 14) mbar_wait_sl(bar_done + (27 + s - (s == 15)) * 8, par);
            const uint32_t fb = bar_full + (32 + s) * 8;
            mbar_expect_tx(fb, SLOT);
            tma_load_2d_mc(sbase + rank * 8192 + (uint32_t)((WO_BSLOT >> (4 * s)) & 15) * SLOT, two, fb, jj * 128 + (int)rank * 64, wslice(jj, s) * 64);
            const int ts = s + par;
            if (s >= 5 && ts < 8) {
              mbar_expect_tx(bar_chk + 104 + ts * 8, SLOT);
              tma_load_2d(sbase + (uint32_t)((WO_ASLOT(par) >> (4 * ts)) & 15) * SLOT, &tm_o, bar_chk + 104 + ts * 8, wslice(jj, ts) * 64, mm * 128);
            }
          }
        }
      }
      __syncwarp();
    } else if (warp == 9) {
      const bool el = elect_one();
      if (el) {
        PROFT(472);
        tma_load_2d(sbase + OFF_S, &tm_x0, bar_full, jj * 128, mm * 128);
        __nanosleep(STAG1);
        tma_load_2d(sbase + OFF_S + SLOT, &tm_x0, bar_full + 8, jj * 128 + 64, mm * 128);
      }
      __syncwarp();
      LOAD_EPOCH();
#pragma unroll 1
      for (int lp = 0; lp < 4 * NLAYERS; lp++) {
        const int l = lp >> 2, ph = lp & 3;
        if (ph == 3) continue;
        const uint32_t par = l & 1;
        const __nv_bfloat16* pb = g_obuf + (ph >> 1) * 64 + (size_t)(mm * 128 + (ph ? 0 : S_LEN) + (lane & 7) * 16 + (jj & 1) * 8) * D_MODEL + (jj >> 1) * 16;
        const CUtensorMap* tm = lp ? &tm_o : &tm_x0;
        const int row = mm * 128 + ((ph || !l) ? 0 : S_LEN);
        const uint32_t bit = ph ? O_BIT(l) : X_BIT(l - 1);
        const uint32_t slots = ph ? (uint32_t)(WO_ASLOT(par) >> (ph * 32 - 28)) : 0x8769876u;
        const unsigned long long fr = ph == 0 ? 0x06050400000000ull : ph == 1 ? (par ? 0x2120353535351Full : 0x22212035351F1Eull) : (par ? 0x27262524232232ull : 0x27262524233232ull);
        uint32_t rdy = (lp == 0 || (lp & 7) == 1) ? 0xFF : 0;
        mbar_wait_sl(ph ? bar_done + ((uint32_t)fr & 63) * 8 : (l ? bar_done + 47 * 8 : bar_full), ph ? par : (l ? par ^ 1 : 0));
#pragma unroll 1
        for (int i = 0; i < (ph == 1 ? 4 + par : 7); i++) {
          if (!((rdy >> i) & 1) && (i < NPOLL || ph == 1)) {
            const unsigned* pp = reinterpret_cast<const unsigned*>(pb + ((jj + i + 1 + ((lane >> 3) & (POLLW - 1))) & 7) * 128);
            if (i == 0) __nanosleep(POLL0);
            unsigned v0 = ld_relaxed(pp);
            __nanosleep(POLLGAP);
            unsigned v1 = ld_relaxed(pp);
            uint32_t no;
#pragma unroll 1
            for (int it = 0; it < (1 << 18); it++) {
              no = __ballot_sync(0xffffffffu, (v0 ^ bit) & 1);
              if (!(no & 0xFF)) break;
              v0 = ld_relaxed(pp);
              no = __ballot_sync(0xffffffffu, (v1 ^ bit) & 1);
              if (!(no & 0xFF)) break;
              v1 = ld_relaxed(pp);
            }
            rdy = ((1 | (no & 0xFF00 ? 0 : 2) | (no & 0xFF0000 ? 0 : 4) | (no >> 24 ? 0 : 8)) & ((1 << POLLW) - 1)) << i;
          }
          if (ph || i >= 4) mbar_wait_sl(bar_done + ((uint32_t)(fr >> (8 * i)) & 63) * 8, par);
          if (el) {
            if (i == 0) PROFT(320 + l * 16 + ph);
            const uint32_t cb = bar_chk + (ph & 1) * 112 + i * 8;
            mbar_expect_tx(cb, SLOT);
            tma_load_2d(sbase + ((slots >> (4 * i)) & 15) * SLOT, tm, cb, ((jj + i + 1) & 7) * 128 + (ph >> 1) * 64, row);
          }
          __syncwarp();
        }
        if (ph == 0 && el) {
          if (l) { wait_flag(&g_flags.xready[l][mm].v, ep1 * 8); fence_proxy_async_global(); }
#pragma unroll 1
          for (int u = 11; u < 34; u++) {
            if (u == 18) u = 22;
            mbar_wait_sl(bar_done + (u - 4) * 8, par);
            if (u == 32) mbar_expect_tx(bar_xr, 2 * SLOT);
            tma_load_2d(sbase + OFF_RA + (u & 3) * SLOT, tm, u < 32 ? bar_full + u * 8 : bar_xr, kslice(jj, u < 18 ? u - 2 : (u < 32 ? u - 20 : u - 32)) * 64, row);
            if (l == 0 && u < 16 && NLAYERS > 1) {
              if (u == 11) { mbar_expect_tx(bar_phi, SLOT + 8192); tma_load_2d(sbase + OFF_PHI, &tm_phi, bar_phi, 0, jj * 128); }
              else tma_load_2d(sbase + 12 * SLOT + (u - 12) * 4096, &tm_wqB, bar_phi, jj * 128 + ((u - 12) >> 1) * 64, mm * 64 + (u & 1) * 32);
            }
          }
        }
        __syncwarp();
      }
      cluster_wait();
    } else {
      const int hw = warp - 10;
      LOAD_EPOCH();
      const bool el = elect_one();
      cluster_wait();
      if (hw == 0) {
        mbar_wait_sl(bar_full + 8, 0);
        if (lane < 7) prefetch_tmap(lane == 0 ? &tm_os : lane == 1 ? &tm_o : lane == 2 ? &tm_wf : lane == 3 ? &tm_wqB : lane == 4 ? &tm_woA : lane == 5 ? &tm_woB : &tm_phi);
        if (lane < 4) asm volatile("prefetch.global.L2 [%0];" :: "l"(prm.wB_phi + jj * 4096 + mm * 256 + lane * 64));
#pragma unroll 1
        for (int i = 0; i < 8; i++) {
          asm volatile("prefetch.global.L2 [%0];" :: "l"(prm.wB_qkv + (size_t)(mm * 64 + (i & 3) * 16 + (lane >> 1)) * 3072 + (i >> 2) * 1024 + jj * 128 + (lane & 1) * 64));
          __nanosleep(PFGAP);
        }
      } else {
#pragma unroll 1
        for (int b = 0; b < 2; b++) {
          float4* z = reinterpret_cast<float4*>(g_kv[b] + (jj * 4) * KVH + mm * (4 * KVH / 16)) + lane;
#pragma unroll
          for (int i = 0; i < 5; i++) z[i * 32] = make_float4(0.f, 0.f, 0.f, 0.f);
        }
#pragma unroll 1
        for (int i = 0; i < 16; i++) {
          const int b = i >> 2;
          const uint32_t v = (b == 0 ? O_BIT(0) : b == 1 ? X_BIT(0) : (NLAYERS > 2 ? 1u : ep1)) + 1;
          uint4* p = b < 2 ? reinterpret_cast<uint4*>(g_obuf + (size_t)(b * S_LEN + mm * 128 + (i & 3) * 32 + (lane >> 3) * 8) * D_MODEL + jj * 128 + (b ? 0 : 64)) + (lane & 7)
                           : g_halo + (size_t)(mm * 8 + jj) * 512 + (i - 8) * 32 + 256 + lane;
          *p = make_uint4(v, v, v, v);
        }
        fence_proxy_async_global();
      }
      __syncwarp();
      uint32_t chkp = 0;
#pragma unroll 1
      for (int lp = 0; lp < 4 * NLAYERS; lp++) {
        const int l = lp >> 2, ph = lp & 3;
        if (ph >= 2 + hw) continue;
        const uint32_t par = l & 1;
        int lane; asm volatile("mov.u32 %0, %%laneid;" : "=r"(lane));
        if (hw) {
          const uint32_t bit = ph ? O_BIT(l) : X_BIT(l - 1);
          const uint32_t slots = ph ? (uint32_t)(WO_ASLOT(par) >> (ph * 32 - 28)) : 0x8769876u;
#pragma unroll 1
          for (int c = 0; c < 7; c++) {
            const uint32_t tile = sbase + ((slots >> (4 * c)) & 15) * SLOT;
            const int cb = c + (ph & 1) * 14;
#pragma unroll 1
            for (int it = 0; it < (1 << 12); it++) {
              mbar_wait_sl(bar_chk + cb * 8, (chkp >> cb) & 1);
              chkp ^= 1u << cb;
              if (el && c == 0) PROFT(ph == 1 ? 480 + l * 2 : 488 + l * 2 + (ph >> 1));
              if (lp == 0) break;
              uint32_t a1 = 1, o1 = 0;
#pragma unroll
              for (int i = 0; i < 16; i++) {
                uint32_t w;
                asm volatile("ld.shared.u32 %0, [%1];" : "=r"(w) : "r"(tile + i * 1024 + (lane & 7) * 132 + (lane >> 3) * 32) : "memory");
                a1 &= w; o1 |= w;
              }
              if (__all_sync(0xffffffffu, ((bit ? a1 : ~o1) & 1) != 0)) break;
              if (el) {
                fence_proxy_async_smem();
                mbar_expect_tx(bar_chk + cb * 8, SLOT);
                tma_load_2d(tile, &tm_o, bar_chk + cb * 8, ((jj + c + 1) & 7) * 128 + (ph >> 1) * 64, mm * 128 + (ph ? 0 : S_LEN));
                RETRY_COUNT();
              }
              __syncwarp();
            }
            if (el) mbar_arrive_local(bar_full + (c + (ph ? 25 + ph * 8 : 4)) * 8);
            __syncwarp();
          }
          if (ph) continue;
#pragma unroll 1
          for (int hp = 0; hp < 2; hp++) {
            const uint4* src = reinterpret_cast<const uint4*>(g_colsum[par][jj * 64 + hp * 32 + lane]);
            uint32_t bad;
            int it = 0;
            float c[6];
            do {
              bad = 0;
#pragma unroll
              for (int p = 0; p < 3; p++) {
                const uint4 v = ld_ll(src + ((par && p < 2) ? (hp ? -32 : 512) + p * 32 : p * 512));
                bad |= (v.y ^ ep1) | (v.w ^ ep1);
                c[2 * p] = __uint_as_float(v.x) + __uint_as_float(v.z); c[2 * p + 1] = __uint_as_float(v.y) + __uint_as_float(v.w);
              }
              bad &= 3;
              if (bad) __nanosleep(300);
            } while (bad && ++it < (1 << 16));
#pragma unroll
            for (int p = 0; p < 6; p++) {
              uint32_t h, m, lo;
              split3(c[p], h, m, lo);
              sts128(sbase + OFF_LNB + hp * 4096 + (p >> 1) * 1024 + lane * 32 + (p & 1) * 16, h | (m << 16), h | (lo << 16), h | (m << 16), lo | (m << 16));
            }
            fence_proxy_async_smem();
            __syncwarp();
            if (el) { mbar_arrive_local(hp ? bar_stat2 : bar_stat); if (hp == 0) PROFT(324 + l * 16); }
            __syncwarp();
          }
          continue;
        } else if (ph == 0) {
          mbar_wait_sl(bar_done + 24, par);
          const uint4* sp = reinterpret_cast<const uint4*>(g_stats + (size_t)(mm * 128) * 8) + lane;
#pragma unroll 1
          for (int hf = 0; hf < 4; hf++) {
            uint4 v[4];
            uint32_t bad;
            int it = 0;
            do {
              bad = 0;
#pragma unroll
              for (int i = 0; i < 4; i++) { v[i] = ld_ll(sp + (hf * 4 + i) * 32); bad |= (v[i].y ^ STAT_TAG(l)) | (v[i].w ^ STAT_TAG(l)); }
              bad &= 3;
              if (bad) __nanosleep(200);
            } while (bad && ++it < (1 << 16));
            __syncwarp();
            float mean = 0.f, m2 = 0.f;
#pragma unroll
            for (int i = 0; i < 4; i++) {
              float a = __uint_as_float(v[i].x) + __uint_as_float(v[i].z);
              a += __shfl_xor_sync(0xffffffffu, a, 1); a += __shfl_xor_sync(0xffffffffu, a, 2);
              a *= 0.125f;
              const float e0 = __uint_as_float(v[i].x) - a, e1 = __uint_as_float(v[i].z) - a;
              float q = fmaf(fmaf(e0, e0, e1 * e1), 128.f, __uint_as_float(v[i].y) + __uint_as_float(v[i].w));
              q += __shfl_xor_sync(0xffffffffu, q, 1); q += __shfl_xor_sync(0xffffffffu, q, 2);
              if ((lane & 3) == i) { mean = a; m2 = q; }
            }
            const uint32_t row = hf * 32 + (lane & 3) * 8 + (lane >> 2);
            uint32_t h, m, lo;
            split3(-0.5f * mean, h, m, lo);
            sts128(sbase + OFF_LNA + row * 16, h | (h << 16), m | (h << 16), lo | (m << 16), m | (lo << 16));
            sts32f(sbase + OFF_ST + row * 4, rsqrtf(m2 * (1.f / 1024.f) + 1e-5f));
          }
          fence_proxy_async_smem();
          __syncwarp();
          if (el) { mbar_arrive_local(bar_stat); PROFT(323 + l * 16); }
          __syncwarp();
#pragma unroll 1
          for (int i = 0; i < 8 - 4 * l; i++) {
            asm volatile("prefetch.global.L2 [%0];" :: "l"(i < 4 ? (l ? prm.wB_o : prm.wA_o) + (size_t)cta * 8192 + i * 2048 + lane * 64
                                                                 : prm.wB_qkv + (size_t)(cta * 8 + (i - 4) * 2 + (lane >> 4)) * 3072 + 2048 + (lane & 15) * 64));
            __nanosleep(PFGAP);
          }
          continue;
        }
        {
          {
            if (l & 1)
#pragma unroll 1
            for (int h = 0; h < 2; h++) {
              asm volatile("bar.sync %0, 288;" :: "r"(BAR_KV + h) : "memory");
              __syncwarp();
              PROFT(331 + l * 16 + h);
              if (lane < 16) signal_release(&g_flags.kvready[(l & 2) + h][jj][lane].v);
              const unsigned* kf = &g_flags.kvready[(l & 2) + h][jj][mm].v;
              unsigned v0 = ld_relaxed(kf);
              __nanosleep(150);
              unsigned v1 = ld_relaxed(kf);
#pragma unroll 1
              for (int it = 0; it < (1 << 18); it++) {
                if (v0 == ep1 * 16) break;
                v0 = ld_relaxed(kf);
                if (v1 == ep1 * 16) break;
                v1 = ld_relaxed(kf);
              }
              fence_acquire();
              __syncwarp();
              if (h) mbar_wait_sl(bar_lx, 1);
              if (el) {
                PROFT(333 + l * 16 + h);
                fence_proxy_async_global();
                mbar_expect_tx(bar_kvf + h * 8, 2 * KVH * 4);
#pragma unroll 1
                for (int i = 0; i < 4; i++)
                  asm volatile("cp.async.bulk.shared::cluster.global.mbarrier::complete_tx::bytes [%0], [%1], %2, [%3];"
                               :: "r"(sbase + ((i & 1) ? OFF_PHI + h * 4096 + (i >> 1) * 2048 : 11 * SLOT + (i >> 1) * 8192)),
                                  "l"(g_kv[l >> 1] + (jj * 4 + h * 2 + (i >> 1)) * KVH + (i & 1) * 2048), "r"((i & 1) ? 2048 : 8192), "r"(bar_kvf + h * 8) : "memory");
              }
              __syncwarp();
            }
          }
#pragma unroll 1
          for (uint32_t ev = l == NLAYERS - 1 ? 0x8u : (l == 0 ? 0x83654u : 0x83u); ev != 8; ev >>= 4) {
            const int e = ev & 15;
            asm volatile("bar.sync %0, 288;" :: "r"((0xFECA987 >> (4 * e)) & 15) : "memory");
            if (el) {
              if (e < 4) {
                PROFT(325 + l * 16 + e);
                tma_store_2d(&tm_o, sbase + 11 * SLOT, jj * 128 + 64, mm * 128 + S_LEN);
              } else {
                if (e == 5) mbar_expect_tx(bar_phi + 8, SLOT);
#pragma unroll 1
                for (int i = 0; i < 4; i++) {
                  const uint32_t a = sbase + (e > 4 ? 10 : 12) * SLOT + i * 4096;
                  const int c0 = (e > 4 ? 1024 : 0) + jj * 128 + (i >> 1) * 64, c1 = mm * 64 + (i & 1) * 32;
                  if (e == 5) tma_load_2d(a, &tm_wqB, bar_phi + 8, c0, c1); else tma_store_2d(&tm_wf, a, c0, c1);
                }
                if (e != 5) {
                  asm volatile("cp.async.bulk.commit_group;\ncp.async.bulk.wait_group.read 0;" ::: "memory");
                  mbar_arrive_local(bar_phi + (e - 4) * 4);
                }
              }
              if ((0x48 >> e) & 1) {
                bulk_commit_wait();
                signal_release(e == 6 ? &g_flags.wfready[jj].v : &g_flags.xready[l + 1][mm].v);
              }
              if (e == 3) PROFT(330 + l * 16);
              if (e == 6) PROFT(335);
            }
            __syncwarp();
          }
        }
      }
    }
    cluster_sync();
  } else {
    asm volatile("setmaxnreg.inc.sync.aligned.u32 232;");
    LOAD_EPOCH();
    const int wg = warp >> 2;
    const int r0 = warp * 16;
    const uint32_t pK = sbase + OFF_S, pV = sbase + OFF_S + SLOT;
#define PMASKS(on, bit) const uint32_t pm0 = ((on) && t == (g & 3) && (g >> 2) == (g & 1)), pm1 = ((on) && t == (g & 3) && (g >> 2) != (g & 1)), pbit = (bit)
#define PBIT0(w) (((w) & ~pm0) | (pbit & pm0))
#define PBIT1(w) (((w) & ~pm1) | (pbit & pm1))
#define LANE_CONSTS() \
    int lane; asm volatile("mov.u32 %0, %%laneid;" : "=r"(lane)); \
    const int g = lane >> 2, t = lane & 3; \
    const uint32_t srowoff = (r0 + (lane & 15)) * 128, lsw = (lane & 7) << 4, lhi = (lane >> 4) << 4, lsw2 = (lane & 6) << 3; \
    (void)g; (void)t; (void)srowoff; (void)lsw; (void)lhi; (void)lsw2;
    uint32_t stgp = 0, peer;
    asm volatile("mapa.shared::cluster.u32 %0, %1, %2;" : "=r"(peer) : "r"(sbase), "r"(rank ^ 1));
    peer -= sbase;
    const uint32_t dA0 = (((sbase & 0x3FFFF) + wg * 8192) >> 4) | 0x10000u, dB0 = ((sbase & 0x3FFFF) >> 4) | 0x2000000u;
    cluster_wait();
#define STG_ARRIVE() { __syncwarp(); if (elect_one()) mbar_arrive_local(bar_stg); }
#define STG_WAIT() { mbar_wait(bar_stg, stgp); stgp ^= 1; }
#define PROFS() do {} while (0)
#define REL(addr) { if (elect_one()) { mbar_arrive_local(addr); asm volatile("mbarrier.arrive.shared::cluster.b64 _, [%0];" :: "r"((addr) + peer) : "memory"); } }
#define QSTEP(ACC, DA, SC, PRE) { \
      const uint32_t da = (DA), db = dB0 + (ub & 0x18) * (QST >> 7); \
      mbar_wait(ub, par); \
      PRE; \
      wgmma_fence(); \
      wgmma4_n192<SC>(ACC, da, db); \
      wgmma_commit(); PROFS(); }
#define QREL() { wgmma_wait<1>(); REL(ub + 376); ub += 8; }
#define RA_CUR (dA0 + (OFF_RA >> 4) + (ub & 0x18) * (SLOT >> 7))
#define PUMP1() { QSTEP(S1, RA_CUR, 1, {}); QREL(); }
#define PUMP0() { PUMP1(); SCHED_FENCE(); }
#define PUMP() if (h == 0) PUMP1()
#define WSTEP() { \
      const uint32_t s4 = (ub - bar_full - 256) >> 1; \
      const uint32_t da = dA0 + (((uint32_t)(WO_ASLOT(par) >> s4) & 15) << 10), db = dB0 + (((uint32_t)(WO_BSLOT >> s4) & 15) << 10); \
      mbar_wait(ub, par); \
      wgmma_fence(); \
      wgmma4_n128<1>(S1, da, db); \
      wgmma_commit(); PROFS(); \
      wgmma_wait<1>(); \
      if (s4) REL(ub + 376); \
      ub += 8; }
#define PUMPS(n) { _Pragma("unroll 1") for (int i_ = 0; i_ < (n); i_++) PUMP1(); }
#define SITE(n) { if ((BMASK >> (n)) & 1) PUMP1(); SCHED_FENCE(); }
#define LNSTEP(ACC, hh) { wgmma_fence(); wgmma_n192<1, 0>(ACC, make_desc(sbase + OFF_LNA + wg * 1024, 0, 128) ^ (1ull << 62), make_desc(sbase + OFF_LNB + (hh) * 4096, 0, 128) ^ (1ull << 62)); }
#define DRAIN_A(ACC, PMP) { \
      LANE_CONSTS(); \
      STAGE64(ACC, 64, pV, 1, 1); \
      PMP; \
      STAGE64(ACC, 32, pK, 0, 1); \
      STG_ARRIVE(); \
      _Pragma("unroll") for (int i_ = 0; i_ < 16; i_++) qa[i_] = pack_bf16(ACC[2 * i_], ACC[2 * i_ + 1]); \
      PINU(qa, 16); }
#define DRAIN_B(ACC) { \
      LANE_CONSTS(); \
      STAGE64(ACC, 64, pV, 1, 0); \
      _Pragma("unroll") for (int i_ = 0; i_ < 64; i_++) st[i_] = ACC[i_]; \
      PIN(st, 64); }
#define WARP_STORE(tm, tile, col, row) { fence_proxy_async_smem(); __syncwarp(); \
      if (elect_one()) { tma_store_2d(tm, (tile) + r0 * 128, col, (row) + r0); asm volatile("cp.async.bulk.commit_group;" ::: "memory"); } __syncwarp(); }
#define PUBLISH_O() WARP_STORE(&tm_os, pO, jj * 128 + h * 64, mm * 128)
#define X_OUT(pc, on) { \
      PMASKS(on, X_BIT(l)); \
      _Pragma("unroll") for (int j = (pc) * 4; j < (pc) * 4 + 4; j++) \
        stsm_x4(pK + (pc) * SLOT + srowoff + ((((uint32_t)(j & 3) << 5) + lhi) ^ lsw), \
                PBIT0(pack_bf16(S1[j * 8 + 0], S1[j * 8 + 1])), PBIT0(pack_bf16(S1[j * 8 + 2], S1[j * 8 + 3])), \
                PBIT1(pack_bf16(S1[j * 8 + 4], S1[j * 8 + 5])), PBIT1(pack_bf16(S1[j * 8 + 6], S1[j * 8 + 7]))); }
#define REST_P1(SKEW, HOOK) { \
      mbar_wait(bar_stat2, par); \
      LNSTEP(S1, 1); \
      _Pragma("unroll 1") while (ub < bar_full + 256) { \
        if (ub == bar_full + 256 - 8 * (SKEW) && wg == 0) bar_sync<BAR_SKEW, 256>(); \
        QSTEP(S1, RA_CUR, 1, {}); \
        if (ub == bar_full + 248 && wg == 1) bar_arrive<BAR_SKEW, 256>(); \
        QREL(); \
      } \
      hbase += 256; \
      HOOK; \
      mbar_wait(bar_done + (31 - (SKEW)) * 8, par);        \
      wgmma_wait<0>(); \
      ACC_FENCE(S1, 96); \
      REL(bar_done + 31 * 8); \
      PROF(13); }
#define FOLD(tile, rd) { \
          LANE_CONSTS(); \
          float d[32]; \
          ACC_DEF(d, 32); \
          mbar_wait(bar_phi + (rd) * 8, 0); \
          wgmma_fence(); \
          _Pragma("unroll") for (int i = 0; i < 2; i++) { \
            const uint64_t da = make_desc((tile) + wg * 8192 + i * 64, 16, 1024); \
            const uint64_t db = make_desc(sbase + OFF_PHI + wg * 4096 + i * 2048, 16, 512) ^ (3ull << 62); \
            wgmma_n32<0>(d + i * 16, da, db); wgmma_n32<1>(d + i * 16, da + 2, db + 64); \
          } \
          wgmma_commit(); \
          PUMP0(); \
          ACC_FENCE(d, 32); \
          bar_wg(wg); \
          _Pragma("unroll") for (int i = 0; i < 4; i++) { \
            const float* x = d + (i & 1) * 8 + (i >> 1) * 2; \
            if (rd) sts128((tile) + wg * 8192 + ((warp & 3) * 16 + (i >> 1) * 8 + g) * 128 + (((2 * t + (i & 1)) ^ g) << 4), \
                           pack_bf16(x[0], x[1]), pack_bf16(x[4], x[5]), pack_bf16(x[16], x[17]), pack_bf16(x[20], x[21])); \
            else stsm_x4((tile) + srowoff + ((((uint32_t)i << 5) + lhi) ^ lsw), pack_bf16(d[i * 8], d[i * 8 + 1]), pack_bf16(d[i * 8 + 2], d[i * 8 + 3]), \
                         pack_bf16(d[i * 8 + 4], d[i * 8 + 5]), pack_bf16(d[i * 8 + 6], d[i * 8 + 7])); \
          } \
          fence_proxy_async_smem(); \
          bar_arrive<BAR_WF + 3 * (rd), 288>(); }
#define LOAD_X0(base) \
      _Pragma("unroll") for (int j = 0; j < 8; j++) { \
        uint32_t x0, x1, x2, x3; \
        ldsm_x4((base) + (j >> 2) * SLOT + srowoff + ((((uint32_t)(j & 3) << 5) + lhi) ^ lsw), x0, x1, x2, x3); \
        S1[j * 8 + 0] = bf_lo(x0); S1[j * 8 + 1] = bf_hi(x0); S1[j * 8 + 2] = bf_lo(x1); S1[j * 8 + 3] = bf_hi(x1); \
        S1[j * 8 + 4] = bf_lo(x2); S1[j * 8 + 5] = bf_hi(x2); S1[j * 8 + 6] = bf_lo(x3); S1[j * 8 + 7] = bf_hi(x3); \
      }
#define LOAD_X() { \
      wgmma_wait<0>(); \
      mbar_wait(bar_xr, par); \
      LOAD_X0(sbase + OFF_RA); \
      ACC_FENCE(S1, 64); \
      __syncwarp(); if (elect_one()) mbar_arrive_local(bar_lx); }

    float S1[96];
#pragma unroll
    for (int i = 0; i < 64; i++) S1[i] = 0.f;
#pragma unroll 1
    for (int l = 0; l < NLAYERS; l++) {
      const uint32_t par = l & 1;
      bar_wg(wg);
      PROF(0);
      uint32_t ub = bar_full;
      const bool hsend = (warp == 7) && (mm < 15);
      const uint32_t hbit = (NLAYERS > 2) ? (l == 0) : (ep1 & 1);
      float S0[96];
      {
        LANE_CONSTS();
        ACC_DEF(S0, 96);
        QSTEP(S0, dA0 + (OFF_S >> 4), 0, {});
        ub += 8;
        PROF(1);
        if (l == 0) { mbar_wait(ub, 0); LOAD_X0(pK); }
        else { X_OUT(1, false); fence_proxy_async_smem(); }
        SCHED_FENCE();
        {
          float a0 = S1[0], a1 = S1[2], b0 = S1[1], b1 = S1[3];
#pragma unroll
          for (int i = 4; i < 64; i += 4) { a0 += S1[i]; b0 += S1[i + 1]; a1 += S1[i + 2]; b1 += S1[i + 3]; }
          a0 += b0; a1 += b1;
          a0 += __shfl_xor_sync(0xffffffffu, a0, 1); a1 += __shfl_xor_sync(0xffffffffu, a1, 1);
          a0 += __shfl_xor_sync(0xffffffffu, a0, 2); a1 += __shfl_xor_sync(0xffffffffu, a1, 2);
          a0 *= (1.f / 128.f); a1 *= (1.f / 128.f);
          asm volatile("" : "+f"(a0), "+f"(a1));
          bar_wg(wg);
          QSTEP(S0, dA0 + ((OFF_S + SLOT) >> 4), 1, wgmma_wait<0>());
          REL(ub + 376); ub += 8;
          SCHED_FENCE();
          float q0 = 0.f, q1 = 0.f;
          b0 = 0.f; b1 = 0.f;
#pragma unroll
          for (int i = 0; i < 64; i += 4) {
            const float d0 = S1[i] - a0, d1 = S1[i + 1] - a0, d2 = S1[i + 2] - a1, d3 = S1[i + 3] - a1;
            q0 = fmaf(d0, d0, q0); b0 = fmaf(d1, d1, b0); q1 = fmaf(d2, d2, q1); b1 = fmaf(d3, d3, b1);
          }
          q0 += b0; q1 += b1;
          q0 += __shfl_xor_sync(0xffffffffu, q0, 1); q1 += __shfl_xor_sync(0xffffffffu, q1, 1);
          q0 += __shfl_xor_sync(0xffffffffu, q0, 2); q1 += __shfl_xor_sync(0xffffffffu, q1, 2);
          if (t < 2) st_b64(g_stats + (size_t)(mm * 128 + r0 + g + t * 8) * 8 + jj, __float_as_uint(t ? a1 : a0), (__float_as_uint(t ? q1 : q0) & ~3u) | STAT_TAG(l));
        }
        if (l) { asm volatile("cp.async.bulk.wait_group 0;" ::: "memory"); bar_arrive<BAR_O + 3, 288>(); }
        ACC_DEF(S1, 96);
        QSTEP(S1, dA0 + (OFF_S >> 4), 0, {});
        QREL();
        QSTEP(S1, dA0 + ((OFF_S + SLOT) >> 4), 1, {});
        QREL();
#pragma unroll 1
        for (int i = 0; i < 14; i++) {
          QSTEP(S0, RA_CUR, 1, {});
          if (i == 0) PROF(2);
          QREL();
        }
      }
      LANE_CONSTS();
      uint4* hbase = g_halo + (size_t)(mm * 8 + jj) * 512;
      mbar_wait(bar_stat, par);
      LNSTEP(S0, 0);
      wgmma_commit();
      const float rs0 = lds32f(sbase + OFF_ST + (r0 + g) * 4), rs1 = lds32f(sbase + OFF_ST + (r0 + g + 8) * 4);
      PUMP0();
      ACC_FENCE(S0, 96);
      PROF(3);
      if (!par) {
        constexpr uint32_t par = 0;
        uint32_t qa[16];
        DRAIN_A(S0, PUMP0());
#pragma unroll 1
        for (int h = 0; h < 2; h++) {
          const uint32_t pO = sbase + (h ? 3 : 12) * SLOT;
          PROF(4 + h * 12);
          const bool fold = (l == 0 && h == 0 && NLAYERS > 1);
          if (fold) FOLD(pO, 0) else if (h == 0) PUMPS(HPUMP1);
          LANE_CONSTS();
          uint4 hv[8];
#pragma unroll
          for (int i = 0; i < 8; i++) hv[i] = make_uint4(hbit, 0, 0, 0);
          const bool hrec = (warp == 0 && mm > 0);
          if (hrec) {
#pragma unroll
            for (int i = 0; i < 8; i++) hv[i] = ld_b128(hbase + lane - 8 * 512 + i * 32);
          }
          if (h) LOAD_X() else PUMPS(HPUMP2);
          const uint32_t halo = sbase + OFF_HALO;
          STG_WAIT();
          if (warp == 0) {
#pragma unroll 1
            for (int it = 0; it < (1 << 16); it++) {
              uint32_t bad = 0;
#pragma unroll
              for (int i = 0; i < 8; i++) bad |= hv[i].x ^ hbit;
              if (__all_sync(0xffffffffu, (bad & 1) == 0)) break;
#pragma unroll
              for (int i = 0; i < 8; i++) hv[i] = ld_b128(hbase + lane - 8 * 512 + i * 32);
            }
#pragma unroll
            for (int i = 0; i < 8; i++)
              stsm_x4(i < 4 ? halo + srowoff + ((((uint32_t)i << 5) + lhi) ^ lsw)
                            : halo + (srowoff >> 1) + (i >> 1) * 1024 + ((((uint32_t)(i & 1) << 5) + lhi) ^ lsw2), hv[i].x, hv[i].y, hv[i].z, hv[i].w);
            __syncwarp();
          }
          PROF(5 + h * 12);
          const uint32_t kb1 = pK + r0 * 128, vb1 = pV + r0 * 64;
          const uint32_t kb0 = r0 ? kb1 - 2048 : halo, vb0 = r0 ? vb1 - 1024 : halo + 2048;
          const uint32_t vhs = r0 ? 8192 : 1024;
          float s[2][4][4];
          {
            uint32_t kf[2][4][4];
#pragma unroll
            for (int i = 0; i < 8; i++) {
              const int hh = i >> 2, jb = i & 3;
              ldsm_x4(((jb < 2) ? kb0 : kb1) + ((jb & 1) * 8 + (lane & 7)) * 128 + ((hh * 64 + ((lane >> 3) << 4)) ^ lsw), kf[hh][jb][0], kf[hh][jb][1], kf[hh][jb][2], kf[hh][jb][3]);
              s[hh][jb][0] = s[hh][jb][1] = s[hh][jb][2] = s[hh][jb][3] = 0.f;
            }
#pragma unroll
            for (int ks = 0; ks < 2; ks++)
#pragma unroll
              for (int i = 0; i < 8; i++) {
                const int hh = i >> 2, jb = i & 3;
                mma_bf16(s[hh][jb], qa[hh * 8 + ks * 4], qa[hh * 8 + ks * 4 + 1], qa[hh * 8 + ks * 4 + 2], qa[hh * 8 + ks * 4 + 3], kf[hh][jb][ks * 2], kf[hh][jb][ks * 2 + 1]);
              }
          }
          PUMP();
          if (fold) bar_arrive<BAR_WF + 2, 288>();
          PROF(6 + h * 12);
          const bool e = g & 1, hb = (2 * t + (g & 1)) <= g;
          uint32_t vf[2][2][2][4];
#pragma unroll
          for (int i = 0; i < 8; i++) {
            const int hh = i >> 2, ks = (i >> 1) & 1, dp = i & 1;
            ldsm_x4_t((ks ? vb1 + hh * 8192 : vb0 + hh * vhs) + (lane & 15) * 64 + ((dp * 32 + lhi) ^ lsw2), vf[hh][ks][dp][0], vf[hh][ks][dp][1], vf[hh][ks][dp][2], vf[hh][ks][dp][3]);
          }
          float va[2][2], vb[2][2], mx[2][2];
#pragma unroll
          for (int hh = 0; hh < 2; hh++) {
            va[hh][0] = e ? s[hh][1][1] : s[hh][1][0];
            vb[hh][0] = hb ? (e ? s[hh][2][1] : s[hh][2][0]) : (e ? s[hh][0][1] : s[hh][0][0]);
            va[hh][1] = e ? s[hh][2][3] : s[hh][2][2];
            vb[hh][1] = hb ? (e ? s[hh][3][3] : s[hh][3][2]) : (e ? s[hh][1][3] : s[hh][1][2]);
          }
          if (warp == 0 && mm == 0) {
#pragma unroll
            for (int hh = 0; hh < 2; hh++) { va[hh][0] = -INFINITY; if (!hb) { vb[hh][0] = -INFINITY; vb[hh][1] = -INFINITY; } }
          }
#pragma unroll
          for (int i = 0; i < 4; i++) mx[i >> 1][i & 1] = fmaxf(va[i >> 1][i & 1], vb[i >> 1][i & 1]);
#pragma unroll
          for (int o = 1; o <= 2; o <<= 1)
#pragma unroll
            for (int i = 0; i < 4; i++) mx[i >> 1][i & 1] = fmaxf(mx[i >> 1][i & 1], __shfl_xor_sync(0xffffffffu, mx[i >> 1][i & 1], o));
          const float sc0 = rs0 * (0.17677669529663687f * LOG2E), sc1 = rs1 * (0.17677669529663687f * LOG2E);
#pragma unroll
          for (int i = 0; i < 4; i++) {
            const float sc = (i & 1) ? sc1 : sc0, m = mx[i >> 1][i & 1];
            va[i >> 1][i & 1] = ex2((va[i >> 1][i & 1] - m) * sc); vb[i >> 1][i & 1] = ex2((vb[i >> 1][i & 1] - m) * sc);
            mx[i >> 1][i & 1] = va[i >> 1][i & 1] + vb[i >> 1][i & 1];
          }
          if (h == 0 && ASITE) { PIN(&va[0][0], 4); PIN(&vb[0][0], 4); PIN(&mx[0][0], 4); PUMP1(); }
#pragma unroll
          for (int o = 1; o <= 2; o <<= 1)
#pragma unroll
            for (int i = 0; i < 4; i++) mx[i >> 1][i & 1] += __shfl_xor_sync(0xffffffffu, mx[i >> 1][i & 1], o);
          const uint32_t selA = e ? 0x1044 : 0x4410, selB = e ? 0x3244 : 0x4432, selL = hb ? 0x4444 : selB, selH = hb ? selB : 0x4444;
          float o[2][4][4];
          uint32_t pa[2][6];
#pragma unroll
          for (int hh = 0; hh < 2; hh++) {
            const float i0 = rcp_fast(mx[hh][0]), i1 = rcp_fast(mx[hh][1]);
            const uint32_t w0 = pack_bf16(va[hh][0] * i0, vb[hh][0] * i0), w1 = pack_bf16(va[hh][1] * i1, vb[hh][1] * i1);
            pa[hh][0] = __byte_perm(w0, 0, selL); pa[hh][1] = __byte_perm(w0, 0, selA); pa[hh][2] = __byte_perm(w1, 0, selL);
            pa[hh][3] = __byte_perm(w0, 0, selH); pa[hh][4] = __byte_perm(w1, 0, selA); pa[hh][5] = __byte_perm(w1, 0, selH);
#pragma unroll
            for (int dj = 0; dj < 4; dj++) { o[hh][dj][0] = o[hh][dj][1] = o[hh][dj][2] = o[hh][dj][3] = 0.f; }
          }
          PROF(7 + h * 12);
#pragma unroll
          for (int i = 0; i < 8; i++) mma_bf16(o[i >> 2][i & 3], pa[i >> 2][0], 0u, pa[i >> 2][1], pa[i >> 2][2], vf[i >> 2][0][(i >> 1) & 1][(i & 1) * 2], vf[i >> 2][0][(i >> 1) & 1][(i & 1) * 2 + 1]);
#pragma unroll
          for (int i = 0; i < 8; i++) mma_bf16(o[i >> 2][i & 3], pa[i >> 2][3], pa[i >> 2][4], 0u, pa[i >> 2][5], vf[i >> 2][1][(i >> 1) & 1][(i & 1) * 2], vf[i >> 2][1][(i >> 1) & 1][(i & 1) * 2 + 1]);
          if (h == 0) PUMP1() else mbar_wait(bar_done + 30 * 8, par);
          if (fold) mbar_wait(bar_phi, 1);
#pragma unroll
          for (int i = 0; i < 4; i++) {
            const int hh = i >> 1, dp = i & 1;
            PMASKS(true, O_BIT(l));
            stsm_x4(pO + srowoff + ((hh * 64 + dp * 32 + lhi) ^ lsw), PBIT0(pack_bf16(o[hh][dp * 2][0], o[hh][dp * 2][1])), PBIT0(pack_bf16(o[hh][dp * 2][2], o[hh][dp * 2][3])),
                    PBIT1(pack_bf16(o[hh][dp * 2 + 1][0], o[hh][dp * 2 + 1][1])), PBIT1(pack_bf16(o[hh][dp * 2 + 1][2], o[hh][dp * 2 + 1][3])));
          }
          PUBLISH_O();
          PROF(11 + h * 12);
          if (h) break;
          if (fold) { PUMPS(FPUMP); FOLD(pK, 1); }
          REST_P1(ASKEW, asm volatile("cp.async.bulk.wait_group.read 0;" ::: "memory"));
          if (fold) mbar_wait(bar_phi + 8, 1);
          DRAIN_A(S1, {});
        }
      } else {
        constexpr uint32_t par = 1;
        float st[64];
        DRAIN_B(S0);
        if (warp < 2) sts128(sbase + OFF_ONES + warp * 512 + lane * 16, 0x3F803F80u, 0x3F803F80u, 0x3F803F80u, 0x3F803F80u);
        const float c0 = rs0 * LOG2E, c1 = rs1 * LOG2E;
#define KV_MMA(vs) { \
          const uint64_t dp = make_desc(wg ? pK : sbase + 12 * SLOT, 16, 1024); \
          const uint64_t dv = (make_desc(sbase + (vs) * SLOT + wg * 8192, OFF_ONES - (vs) * SLOT - wg * 8192, 512) ^ (3ull << 62)); \
          constexpr uint64_t DVS = 64ull - (64ull << 16); \
          STG_WAIT(); \
          wgmma_fence(); \
          _Pragma("unroll") for (int ks = 0; ks < 8; ks++) { if (ks == 0) wgmma_n40<0, 1>(kv, dp, dv); else wgmma_n40<1, 1>(kv, dp + ks * 128, dv + ks * DVS); } \
          wgmma_commit(); }
#define KV_RED(hp) { \
          float* kvg = g_kv[l >> 1] + (jj * 4 + (hp) * 2 + wg) * KVH + ((warp & 3) * 32 + lane) * 4; \
          _Pragma("unroll") for (int i = 0; i < 4; i++) red_v4(kvg + i * 512, kv[i * 4], kv[i * 4 + 1], kv[i * 4 + 2], kv[i * 4 + 3]); \
          if (t == 0) red_v4(kvg + 2048, kv[16], kv[17], kv[18], kv[19]); \
          bar_arrive<BAR_KV + (hp), 288>(); }
#define KV_TILE(hp) { \
          LANE_CONSTS(); \
          float4 v[5]; \
          mbar_wait(bar_kvf + (hp) * 8, l >> 1); \
          PROF(25 + (hp)); \
          _Pragma("unroll") for (int i = 0; i < 5; i++) \
            asm volatile("ld.shared.v4.f32 {%0, %1, %2, %3}, [%4];" : "=f"(v[i].x), "=f"(v[i].y), "=f"(v[i].z), "=f"(v[i].w) \
                         : "r"(i < 4 ? pV + wg * 8192 + i * 2048 + (warp & 3) * 512 + lane * 16 : sbase + OFF_PHI + (hp) * 4096 + warp * 512 + g * 64) : "memory"); \
          bar_wg(wg); \
          const uint32_t e = lane & 7, jt = ((lane >> 1) & 4) + (e >> 1); \
          const uint32_t row = ((((warp >> 1) ^ wg) & 1) << 5) + ((jt & 1) << 4) + ((warp & 1) << 3) + (jt & 6) + (e & 1); \
          const uint32_t kd = pV + wg * 8192 + row * 128, ksw = (row & 7) << 4; \
          _Pragma("unroll") for (int i = 0; i < 2; i++) { \
            const float4 a = v[i * 2], b = v[i * 2 + 1]; \
            stsm_x4(kd + ((i * 32 + lhi) ^ ksw), pack_bf16(a.x, a.y), pack_bf16(a.z, a.w), pack_bf16(b.x, b.y), pack_bf16(b.z, b.w)); \
          } \
          stsm_x4(kd + ((64u + lhi) ^ ksw), pack_bf16(v[4].x, 1.f), pack_bf16(v[4].z, 1.f), 0u, 0u); }
#pragma unroll 1
        for (int h = 0; h < 2; h++) {
          PROF(4 + h * 2);
          SITE(0);
          LANE_CONSTS();
          const uint32_t dsw = (uint32_t)(g ^ (2 * t)) << 4, dst = ((t & 2) ? pK : sbase + 12 * SLOT) + (r0 + g) * 128;
          float e[16], f[16];
          float mn0 = rmin16(st);
          asm volatile("" : "+f"(mn0)); SCHED_FENCE();
          float sa = exps16(e, st, -c0, mn0 * c0), mx0 = rmax16(st);
          asm volatile("" : "+f"(sa), "+f"(mx0)); PIN(e, 16); SITE(1);
          if (h) STG_WAIT();
          store16(e, sa, dst, dsw, 4);
          float sb = exps16(f, st, c0, -mx0 * c0), mn1 = rmin16(st + 2);
          asm volatile("" : "+f"(sb), "+f"(mn1)); PIN(f, 16); SITE(2);
          store16(f, sb, dst, dsw, 0);
          float sc = exps16(e, st + 2, -c1, mn1 * c1), mx1 = rmax16(st + 2);
          asm volatile("" : "+f"(sc), "+f"(mx1)); PIN(e, 16); SITE(3);
          store16(e, sc, dst + 1024, dsw, 4);
          float sd = exps16(f, st + 2, c1, -mx1 * c1);
          asm volatile("" : "+f"(sd)); PIN(f, 16); SITE(4);
          store16(f, sd, dst + 1024, dsw, 0);
          PROF(5 + h * 2);
          if (h) break;
          {
            float kv[20];
            ACC_DEF(kv, 20);
            fence_proxy_async_smem();
            STG_ARRIVE();
            KV_MMA(11);
            PUMP0();
            ACC_FENCE(kv, 20);
            KV_RED(0);
            STG_ARRIVE();
          }
#pragma unroll
          for (int i = 0; i < 32; i++) st[i] = st[32 + i];
        }
        float mq[8];
        {
          float kv[20];
          mbar_wait(bar_stat2, par);
          LNSTEP(S1, 1);
          ub = bar_full + 240;
          PUMP1();
          if (wg == 0) bar_sync<BAR_SKEW, 256>();
          QSTEP(S1, RA_CUR, 1, {});
          if (wg == 1) bar_arrive<BAR_SKEW, 256>();
          if (KT0) QREL();
          KV_TILE(0);
          if (!KT0) QREL();
          mbar_wait(bar_done + 30 * 8, par);
          wgmma_wait<0>();
          ACC_FENCE(S1, 96);
          REL(bar_done + 31 * 8);
          PROF(13);
          LANE_CONSTS();
          STAGE64(S1, 64, sbase + 3 * SLOT, 1, 0);
          fence_proxy_async_smem();
          STG_ARRIVE();
#pragma unroll
          for (int i = 0; i < 32; i++) st[i] = S1[i];
          PIN(st, 32);
          PROF(16);
          ACC_DEF(kv, 20);
          KV_MMA(3);
          SCHED_FENCE();
          extrema(mq, st, c0, c1);
          PIN(mq, 8);
          wgmma_wait<0>();
          ACC_FENCE(kv, 20);
          KV_RED(1);
          PROF(17);
        }
#pragma unroll 1
        for (int h = 0; h < 2; h++) {
          const uint32_t pO = sbase + (h ? 3 : 8) * SLOT;
          LANE_CONSTS();
          uint32_t fq[32];
          expp16(fq, st, -c0, mq[0], -c1, mq[1]); expp16(fq + 8, st, c0, mq[2], c1, mq[3]); PINU(fq, 16);
          PROF(18 + h * 14);
          if (h) {
            asm volatile("cp.async.bulk.wait_group.read 0;" ::: "memory");
            uint32_t n;
#pragma unroll 1
            while (ub < bar_full + 8 * FILL) {
              int it = 0;
              do {
                asm volatile("{\n.reg .pred p, q;\nsetp.ne.u32 q, %4, 0;\nmbarrier.test_wait.parity.shared::cta.b64 p, [%1], %2;\nand.pred p, p, q;\n"
                             "barrier.red.popc.aligned.u32 %0, %3, 128, p;\n}\n"
                             : "=r"(n) : "r"((warp & 3) ? ub : bar_kvf + 8), "r"((warp & 3) ? par : l >> 1), "r"(2 + wg), "r"((warp & 3) | (uint32_t)(lane == 0)) : "memory");
                n = __shfl_sync(0xffffffffu, n, 0);
              } while (n == 0 && ++it < (1 << 20));
              if (n & 1) break;
              WSTEP();
            }
            KV_TILE(1);
            fence_proxy_async_smem();
            STG_ARRIVE();
          }
          SCHED_FENCE();
          expp16(fq + 16, st + 16, -c0, mq[4], -c1, mq[5]); PINU(fq + 16, 8);
          if (h) STG_WAIT();
          wgmma_wait<0>();
          ACC_FENCE(S1, 64);
          PROF(19 + h * 14);
          float o[4][20];
#define O_MMA(hh) { \
            const uint64_t db = make_desc(pV + (hh) * 8192, 16, 1024); \
            ACC_DEF(o[(hh) * 2], 20); ACC_DEF(o[(hh) * 2 + 1], 20); \
            wgmma_fence(); \
            wgmma_n40_rs<0>(o[(hh) * 2], fq + (hh) * 16, db + 256); wgmma_n40_rs<0>(o[(hh) * 2 + 1], fq + (hh) * 16 + 8, db); \
            wgmma_n40_rs<1>(o[(hh) * 2], fq + (hh) * 16 + 4, db + 384); wgmma_n40_rs<1>(o[(hh) * 2 + 1], fq + (hh) * 16 + 12, db + 128); \
            wgmma_commit(); }
          O_MMA(0);
          SCHED_FENCE();
          expp16(fq + 24, st + 16, c0, mq[6], c1, mq[7]); PINU(fq + 24, 8);
          PMASKS(true, O_BIT(l));
#pragma unroll
          for (int hh = 0; hh < 2; hh++) {
            if (hh && !OW) O_MMA(1);
            wgmma_wait<0>();
            ACC_FENCE(o[hh * 2], 20); ACC_FENCE(o[hh * 2 + 1], 20);
            if (!hh && OW) { O_MMA(1); SCHED_FENCE(); }
            const float* x = o[hh * 2];
            const float* y = o[hh * 2 + 1];
            const float rx0 = rcp_fast(x[17]), ry0 = rcp_fast(y[17]), rx1 = rcp_fast(x[19]), ry1 = rcp_fast(y[19]);
            const float i0 = rcp_fast(fmaf(x[16], rx0, y[16] * ry0) + 1e-6f), i1 = rcp_fast(fmaf(x[18], rx1, y[18] * ry1) + 1e-6f);
            const float ax0 = rx0 * i0, ay0 = ry0 * i0, ax1 = rx1 * i1, ay1 = ry1 * i1;
#pragma unroll
            for (int dp = 0; dp < 2; dp++)
              stsm_x4(pO + srowoff + ((hh * 64 + dp * 32 + lhi) ^ lsw),
                      PBIT0(pack_bf16(fmaf(x[dp * 8], ax0, y[dp * 8] * ay0), fmaf(x[dp * 8 + 1], ax0, y[dp * 8 + 1] * ay0))),
                      PBIT0(pack_bf16(fmaf(x[dp * 8 + 2], ax1, y[dp * 8 + 2] * ay1), fmaf(x[dp * 8 + 3], ax1, y[dp * 8 + 3] * ay1))),
                      PBIT1(pack_bf16(fmaf(x[dp * 8 + 4], ax0, y[dp * 8 + 4] * ay0), fmaf(x[dp * 8 + 5], ax0, y[dp * 8 + 5] * ay0))),
                      PBIT1(pack_bf16(fmaf(x[dp * 8 + 6], ax1, y[dp * 8 + 6] * ay1), fmaf(x[dp * 8 + 7], ax1, y[dp * 8 + 7] * ay1))));
          }
          PUBLISH_O();
          PROF(20 + h * 14);
          if (h) break;
#pragma unroll
          for (int i = 0; i < 32; i++) st[i] = S1[32 + i];
          PIN(st, 32);
          LOAD_X();
          bar_wg(wg);
          WSTEP();
          SCHED_FENCE();
          extrema(mq, st, c0, c1);
          PIN(mq, 8);
          PROF(31);
        }
      }
      __syncwarp();
      if (elect_one()) mbar_arrive_local(bar_epi);
      bar_wg(wg);
#pragma unroll 1
      while (ub < bar_full + 384) {
        WSTEP();
        if (ub == bar_full + 8 * 41) { asm volatile("cp.async.bulk.wait_group.read 0;" ::: "memory"); PROF(35); }
        if (ub == bar_full + 8 * 42) PROF(36);
      }
      wgmma_wait<0>();
      ACC_FENCE(S1, 64);
      REL(bar_done + 47 * 8);
      PROF(37);
      {
        LANE_CONSTS();
        X_OUT(0, l < NLAYERS - 1);
        WARP_STORE(l < NLAYERS - 1 ? &tm_os : &tm_xo, pK, jj * 128, mm * 128 + (l < NLAYERS - 1 ? S_LEN : 0));
        if (l == NLAYERS - 1) {
          X_OUT(1, false);
          WARP_STORE(&tm_xo, pV, jj * 128 + 64, mm * 128);
          asm volatile("cp.async.bulk.wait_group 0;" ::: "memory");
        }
      }
#pragma unroll
      for (int i = 32; i < 64; i++) { uint32_t c; asm volatile("mov.b32 %0, %1;" : "=r"(c) : "f"(S1[i])); S1[i] = __uint_as_float(c); }
      PROF(38);
    }
    const int tid = threadIdx.x;
    if (tid == 0) {
      unsigned old = atomicAdd(&g_flags.done.v, 1);
      if (old == ep1 * NMAIN - 1) {
        asm volatile("st.relaxed.gpu.global.u32 [%0], %1;" :: "l"(&g_flags.epoch.v), "r"(ep1) : "memory");
      }
    }
    __syncwarp();
    cluster_sync();
  }
}

typedef CUresult (*PFN_encode)(CUtensorMap*, CUtensorMapDataType, cuuint32_t, void*, const cuuint64_t*, const cuuint64_t*,
                               const cuuint32_t*, const cuuint32_t*, CUtensorMapInterleave, CUtensorMapSwizzle,
                               CUtensorMapL2promotion, CUtensorMapFloatOOBfill);

CUtensorMap make_map(PFN_encode enc, const void* ptr, uint64_t inner, uint64_t outer, uint32_t box_inner, uint32_t box_outer,
                     CUtensorMapSwizzle swz = CU_TENSOR_MAP_SWIZZLE_128B) {
  CUtensorMap m;
  cuuint64_t dims[2] = {inner, outer};
  cuuint64_t strides[1] = {inner * 2};
  cuuint32_t box[2] = {box_inner, box_outer};
  cuuint32_t es[2] = {1, 1};
  enc(&m, CU_TENSOR_MAP_DATA_TYPE_BFLOAT16, 2, const_cast<void*>(ptr), dims, strides, box, es, CU_TENSOR_MAP_INTERLEAVE_NONE,
      swz, CU_TENSOR_MAP_L2_PROMOTION_L2_256B, CU_TENSOR_MAP_FLOAT_OOB_FILL_NONE);
  return m;
}

}

extern "C" void kernel_launch(void* const* d_in, const int* in_sizes, int n_in, void* d_out, int out_size) {
  (void)in_sizes; (void)n_in; (void)out_size;
  static PFN_encode enc = nullptr;
  if (!enc) {
    void* fn = nullptr;
    cudaDriverEntryPointQueryResult qr;
    cudaGetDriverEntryPoint("cuTensorMapEncodeTiled", &fn, cudaEnableDefault, &qr);
    enc = (PFN_encode)fn;
    cudaFuncSetAttribute(mega_kernel, cudaFuncAttributeMaxDynamicSharedMemorySize, SMEM_BYTES);
  }
  Params prm;
  prm.x0 = (const __nv_bfloat16*)d_in[0];
  prm.wA_qkv = (const __nv_bfloat16*)d_in[1];
  prm.wA_o = (const __nv_bfloat16*)d_in[2];
  prm.wB_qkv = (const __nv_bfloat16*)d_in[4];
  prm.wB_phi = (const __nv_bfloat16*)d_in[5];
  prm.wB_o = (const __nv_bfloat16*)d_in[6];
  prm.out = (__nv_bfloat16*)d_out;
  void *obuf = nullptr, *wf = nullptr;
  cudaGetSymbolAddress(&obuf, g_obuf);
  cudaGetSymbolAddress(&wf, g_wfold);
  CUtensorMap tm_x0 = make_map(enc, d_in[0], D_MODEL, S_LEN, 64, 128);
  CUtensorMap tm_xo = make_map(enc, d_out, D_MODEL, S_LEN, 64, 16);
  CUtensorMap tm_os = make_map(enc, obuf, D_MODEL, 2 * S_LEN, 64, 16);
  CUtensorMap tm_o = make_map(enc, obuf, D_MODEL, 2 * S_LEN, 64, 128);
  CUtensorMap tm_wf = make_map(enc, wf, 2048, D_MODEL, 64, 32);
  CUtensorMap tm_wqA = make_map(enc, d_in[1], 3 * D_MODEL, D_MODEL, 64, 32);
  CUtensorMap tm_wqB = make_map(enc, prm.wB_qkv, 3 * D_MODEL, D_MODEL, 64, 32);
  CUtensorMap tm_woA = make_map(enc, prm.wA_o, D_MODEL, D_MODEL, 64, 64);
  CUtensorMap tm_woB = make_map(enc, prm.wB_o, D_MODEL, D_MODEL, 64, 64);
  CUtensorMap tm_phi = make_map(enc, prm.wB_phi, 32, 1024, 32, 128, CU_TENSOR_MAP_SWIZZLE_64B);
  mega_kernel<<<NMAIN + NAUX, 384, SMEM_BYTES>>>(tm_x0, tm_xo, tm_os, tm_o, tm_wf, tm_wqA, tm_wqB, tm_woA, tm_woB, tm_phi, prm);
}
```

```cpp
#include <cuda_runtime.h>
#include <cuda.h>
#include <cuda_bf16.h>
#include <stdint.h>

#define NLAYERS 4

#define STAG1 300
#define HPUMP1 2
#define HPUMP2 2
#define ASKEW 2
#define FPUMP 2
#define PFGAP 100
#define POLLW 4
#define POLL0 0
#define POLLGAP 120
#define OW 1
#define KT0 0
#define NPOLL 4
#define AW0 0
#define RLATE 0
#define FILL 40
#define BMASK 0x1F
#define ASITE 1
namespace {

constexpr int S_LEN = 2048, D_MODEL = 1024;
constexpr int NAUX = 4, NMAIN = 128;
constexpr int SLOT = 16384;
constexpr int QST = 24576;
constexpr int OFF_RA = 6 * SLOT, OFF_S = 10 * SLOT;
constexpr int OFF_HALO = 13 * SLOT, OFF_LNB = OFF_HALO  , OFF_ONES = OFF_HALO + 3072;
constexpr int OFF_ST = OFF_HALO + 7168  , OFF_PHI = OFF_HALO + 8192;
constexpr int OFF_BAR = 14 * SLOT;
constexpr int OFF_LNA = OFF_BAR + 1024;
constexpr int SMEM_BYTES = OFF_LNA + 2048;
#define WO_ASLOT(par) ((par) ? 0x9876CAB39876CA98ull : 0x98C76BA398C7698Cull)
constexpr unsigned long long WO_BSLOT = 0x5432105421054210ull;
__device__ __forceinline__ int kslice(int j, int i) { return i < 2 ? 2 * j + i : (i < 9 ? 2 * ((j + i - 1) & 7) : 2 * ((j + i) & 7) + 1); }
__device__ __forceinline__ int wslice(int j, int s) { return 2 * ((j + s) & 7) + (s >> 3); }
constexpr int KVH = 5 * 128 * 4;

struct __align__(128) Flag { unsigned v; unsigned pad[31]; };
struct Flags {
  Flag xready[4][16];
  Flag kvready[4][8][16];
  Flag wfready[8];
  Flag done;
  Flag epoch;
};

__device__ Flags g_flags;
__device__ __nv_bfloat16 g_obuf[2 * S_LEN * D_MODEL];
#define O_BIT(l) ((epoch * NLAYERS + (l) + 1) & 1u)
#define X_BIT(l) ((epoch * (NLAYERS - 1) + (l) + 1) & 1u)
__device__ __nv_bfloat16 g_wfold[D_MODEL * 2048];
__device__ uint4 g_halo[16 * 8 * 512];
__device__ float g_kv[2][32 * KVH];
__device__ __align__(128) uint2 g_colsum[2][1536][2];
__device__ __align__(128) uint2 g_stats[S_LEN * 8];
#define STAT_TAG(l) ((ep1 * NLAYERS + (l) + 1) & 3u)

#define RETRY_COUNT()
#define PROFL 1
#define PROFW 0
#define KVFLAG 1
#define PROFT(i) do {} while (0)
#define PROF(i) do {} while (0)

__device__ __forceinline__ uint32_t smem_u32(const void* p) { return (uint32_t)__cvta_generic_to_shared(p); }
__device__ __forceinline__ bool elect_one() {
  uint32_t p;
  asm volatile("{\n.reg .pred p;\nelect.sync _|p, 0xffffffff;\nselp.u32 %0, 1, 0, p;\n}\n" : "=r"(p));
  return p != 0;
}
__device__ __forceinline__ void mbar_init(uint32_t bar, uint32_t cnt) {
  asm volatile("mbarrier.init.shared::cta.b64 [%0], %1;" :: "r"(bar), "r"(cnt));
}
__device__ __forceinline__ void mbar_expect_tx(uint32_t bar, uint32_t bytes) {
  asm volatile("mbarrier.arrive.expect_tx.shared::cta.b64 _, [%0], %1;" :: "r"(bar), "r"(bytes) : "memory");
}
#define mbar_wait(bar, parity) \
  asm volatile("{\n.reg .pred p, q;\nW_%=:\nmbarrier.try_wait.parity.shared::cta.b64 p, [%1], %2;\nadd.s32 %0, %0, -1;\n" \
               "setp.gt.and.s32 q, %0, 0, !p;\n@q bra.uni W_%=;\n}\n" : "+r"(budget) : "r"((uint32_t)(bar)), "r"((uint32_t)(parity)) : "memory")
#define mbar_wait_sl(bar, parity) \
  asm volatile("{\n.reg .pred p, q;\nW_%=:\nmbarrier.try_wait.parity.shared::cta.b64 p, [%1], %2, 20000;\nadd.s32 %0, %0, -64;\n" \
               "setp.gt.and.s32 q, %0, 0, !p;\n@q bra.uni W_%=;\n}\n" : "+r"(budget) : "r"((uint32_t)(bar)), "r"((uint32_t)(parity)) : "memory")
__device__ __forceinline__ void mbar_arrive_local(uint32_t bar) {
  asm volatile("mbarrier.arrive.shared::cta.b64 _, [%0];" :: "r"(bar) : "memory");
}
__device__ __forceinline__ void tma_load_2d(uint32_t dst, const CUtensorMap* tm, uint32_t bar, int c0, int c1) {
  asm volatile("cp.async.bulk.tensor.2d.shared::cluster.global.mbarrier::complete_tx::bytes [%0], [%1, {%3, %4}], [%2];"
               :: "r"(dst), "l"(tm), "r"(bar), "r"(c0), "r"(c1) : "memory");
}
__device__ __forceinline__ void tma_load_2d_mc(uint32_t dst, const CUtensorMap* tm, uint32_t bar, int c0, int c1) {
  asm volatile("cp.async.bulk.tensor.2d.shared::cluster.global.mbarrier::complete_tx::bytes.multicast::cluster [%0], [%1, {%3, %4}], [%2], %5;"
               :: "r"(dst), "l"(tm), "r"(bar), "r"(c0), "r"(c1), "h"((uint16_t)3) : "memory");
}
__device__ __forceinline__ void tma_store_2d(const CUtensorMap* tm, uint32_t src, int c0, int c1) {
  asm volatile("cp.async.bulk.tensor.2d.global.shared::cta.bulk_group [%0, {%2, %3}], [%1];"
               :: "l"(tm), "r"(src), "r"(c0), "r"(c1) : "memory");
}
__device__ __forceinline__ void bulk_commit_wait() {
  asm volatile("cp.async.bulk.commit_group;\ncp.async.bulk.wait_group 0;" ::: "memory");
}
__device__ __forceinline__ void prefetch_tmap(const CUtensorMap* tm) {
  asm volatile("prefetch.tensormap [%0];" :: "l"(tm) : "memory");
}
__device__ __forceinline__ void fence_proxy_async_global() { asm volatile("fence.proxy.async.global;" ::: "memory"); }
__device__ __forceinline__ void fence_proxy_async_smem() { asm volatile("fence.proxy.async.shared::cta;" ::: "memory"); }
__device__ __forceinline__ unsigned ld_relaxed(const unsigned* p) {
  unsigned v;
  asm volatile("ld.relaxed.gpu.global.u32 %0, [%1];" : "=r"(v) : "l"(p) : "memory");
  return v;
}
__device__ __forceinline__ void fence_acquire() { asm volatile("fence.acquire.gpu;" ::: "memory"); }
__device__ __forceinline__ void wait_flag(const unsigned* p, unsigned target) {
  int it = 0;
  while ((int)(ld_relaxed(p) - target) < 0 && ++it < (1 << 20)) {}
  fence_acquire();
}
__device__ __forceinline__ void signal_release(unsigned* p) {
  asm volatile("red.release.gpu.global.add.u32 [%0], 1;" :: "l"(p) : "memory");
}
template <int ID, int N> __device__ __forceinline__ void bar_arrive() { asm volatile("bar.arrive %0, %1;" :: "n"(ID), "n"(N) : "memory"); }
template <int ID, int N> __device__ __forceinline__ void bar_sync() { asm volatile("bar.sync %0, %1;" :: "n"(ID), "n"(N) : "memory"); }
__device__ __forceinline__ void bar_wg(int wg) { asm volatile("bar.sync %0, 128;" :: "r"(2 + wg) : "memory"); }
__device__ __forceinline__ void cluster_sync() {
  asm volatile("barrier.cluster.arrive.relaxed.aligned;\nbarrier.cluster.wait.aligned;" ::: "memory");
}
__device__ __forceinline__ void cluster_wait() { asm volatile("barrier.cluster.wait.acquire.aligned;" ::: "memory"); }
enum { BAR_KV = 4  , BAR_O = 7  , BAR_WF = 12  , BAR_SKEW = 13 };

__device__ __forceinline__ void wgmma_fence() { asm volatile("wgmma.fence.sync.aligned;" ::: "memory"); }
__device__ __forceinline__ void wgmma_commit() { asm volatile("wgmma.commit_group.sync.aligned;" ::: "memory"); }
template <int N> __device__ __forceinline__ void wgmma_wait() { asm volatile("wgmma.wait_group.sync.aligned %0;" :: "n"(N) : "memory"); }

template <int scale_d, int tnsp_b = 1> __device__ __forceinline__ void wgmma_n192(float* d, uint64_t descA, uint64_t descB) {
  asm volatile("{\n.reg .pred p;\nsetp.ne.b32 p, %98, 0;\n"
               "wgmma.mma_async.sync.aligned.m64n192k16.f32.bf16.bf16 {%0,%1,%2,%3,%4,%5,%6,%7,%8,%9,%10,%11,%12,%13,%14,%15,%16,%17,%18,%19,%20,%21,%22,%23,%24,%25,%26,%27,%28,%29,%30,%31,%32,%33,%34,%35,%36,%37,%38,%39,%40,%41,%42,%43,%44,%45,%46,%47,%48,%49,%50,%51,%52,%53,%54,%55,%56,%57,%58,%59,%60,%61,%62,%63,%64,%65,%66,%67,%68,%69,%70,%71,%72,%73,%74,%75,%76,%77,%78,%79,%80,%81,%82,%83,%84,%85,%86,%87,%88,%89,%90,%91,%92,%93,%94,%95}, %96, %97, p, 1, 1, 0, %99;\n}\n"
               : "+f"(d[0]), "+f"(d[1]), "+f"(d[2]), "+f"(d[3]), "+f"(d[4]), "+f"(d[5]), "+f"(d[6]), "+f"(d[7]), "+f"(d[8]), "+f"(d[9]), "+f"(d[10]), "+f"(d[11]), "+f"(d[12]), "+f"(d[13]), "+f"(d[14]), "+f"(d[15]), "+f"(d[16]), "+f"(d[17]), "+f"(d[18]), "+f"(d[19]), "+f"(d[20]), "+f"(d[21]), "+f"(d[22]), "+f"(d[23]), "+f"(d[24]), "+f"(d[25]), "+f"(d[26]), "+f"(d[27]), "+f"(d[28]), "+f"(d[29]), "+f"(d[30]), "+f"(d[31]), "+f"(d[32]), "+f"(d[33]), "+f"(d[34]), "+f"(d[35]), "+f"(d[36]), "+f"(d[37]), "+f"(d[38]), "+f"(d[39]), "+f"(d[40]), "+f"(d[41]), "+f"(d[42]), "+f"(d[43]), "+f"(d[44]), "+f"(d[45]), "+f"(d[46]), "+f"(d[47]), "+f"(d[48]), "+f"(d[49]), "+f"(d[50]), "+f"(d[51]), "+f"(d[52]), "+f"(d[53]), "+f"(d[54]), "+f"(d[55]), "+f"(d[56]), "+f"(d[57]), "+f"(d[58]), "+f"(d[59]), "+f"(d[60]), "+f"(d[61]), "+f"(d[62]), "+f"(d[63]), "+f"(d[64]), "+f"(d[65]), "+f"(d[66]), "+f"(d[67]), "+f"(d[68]), "+f"(d[69]), "+f"(d[70]), "+f"(d[71]), "+f"(d[72]), "+f"(d[73]), "+f"(d[74]), "+f"(d[75]), "+f"(d[76]), "+f"(d[77]), "+f"(d[78]), "+f"(d[79]), "+f"(d[80]), "+f"(d[81]), "+f"(d[82]), "+f"(d[83]), "+f"(d[84]), "+f"(d[85]), "+f"(d[86]), "+f"(d[87]), "+f"(d[88]), "+f"(d[89]), "+f"(d[90]), "+f"(d[91]), "+f"(d[92]), "+f"(d[93]), "+f"(d[94]), "+f"(d[95])
               : "l"(descA), "l"(descB), "n"(scale_d), "n"(tnsp_b));
}
template <int scale_d> __device__ __forceinline__ void wgmma4_n192(float* d, uint32_t da, uint32_t db) {
#define R_ "{%0,%1,%2,%3,%4,%5,%6,%7,%8,%9,%10,%11,%12,%13,%14,%15,%16,%17,%18,%19,%20,%21,%22,%23,%24,%25,%26,%27,%28,%29,%30,%31,%32,%33,%34,%35,%36,%37,%38,%39,%40,%41,%42,%43,%44,%45,%46,%47,%48,%49,%50,%51,%52,%53,%54,%55,%56,%57,%58,%59,%60,%61,%62,%63,%64,%65,%66,%67,%68,%69,%70,%71,%72,%73,%74,%75,%76,%77,%78,%79,%80,%81,%82,%83,%84,%85,%86,%87,%88,%89,%90,%91,%92,%93,%94,%95}"
  asm volatile("{\n.reg .pred p, q;\n.reg .b64 a, b;\nsetp.ne.b32 p, %98, 0;\nsetp.eq.b32 q, 0, 0;\nmov.b64 a, {%96, 0x40000040};\nmov.b64 b, {%97, 0x40000040};\n"
               "wgmma.mma_async.sync.aligned.m64n192k16.f32.bf16.bf16 " R_ ", a, b, p, 1, 1, 0, 1;\nadd.s64 a, a, 2;\nadd.s64 b, b, 128;\n"
               "wgmma.mma_async.sync.aligned.m64n192k16.f32.bf16.bf16 " R_ ", a, b, q, 1, 1, 0, 1;\nadd.s64 a, a, 2;\nadd.s64 b, b, 128;\n"
               "wgmma.mma_async.sync.aligned.m64n192k16.f32.bf16.bf16 " R_ ", a, b, q, 1, 1, 0, 1;\nadd.s64 a, a, 2;\nadd.s64 b, b, 128;\n"
               "wgmma.mma_async.sync.aligned.m64n192k16.f32.bf16.bf16 " R_ ", a, b, q, 1, 1, 0, 1;\n}\n"
               : "+f"(d[0]), "+f"(d[1]), "+f"(d[2]), "+f"(d[3]), "+f"(d[4]), "+f"(d[5]), "+f"(d[6]), "+f"(d[7]), "+f"(d[8]), "+f"(d[9]), "+f"(d[10]), "+f"(d[11]), "+f"(d[12]), "+f"(d[13]), "+f"(d[14]), "+f"(d[15]), "+f"(d[16]), "+f"(d[17]), "+f"(d[18]), "+f"(d[19]), "+f"(d[20]), "+f"(d[21]), "+f"(d[22]), "+f"(d[23]), "+f"(d[24]), "+f"(d[25]), "+f"(d[26]), "+f"(d[27]), "+f"(d[28]), "+f"(d[29]), "+f"(d[30]), "+f"(d[31]), "+f"(d[32]), "+f"(d[33]), "+f"(d[34]), "+f"(d[35]), "+f"(d[36]), "+f"(d[37]), "+f"(d[38]), "+f"(d[39]), "+f"(d[40]), "+f"(d[41]), "+f"(d[42]), "+f"(d[43]), "+f"(d[44]), "+f"(d[45]), "+f"(d[46]), "+f"(d[47]), "+f"(d[48]), "+f"(d[49]), "+f"(d[50]), "+f"(d[51]), "+f"(d[52]), "+f"(d[53]), "+f"(d[54]), "+f"(d[55]), "+f"(d[56]), "+f"(d[57]), "+f"(d[58]), "+f"(d[59]), "+f"(d[60]), "+f"(d[61]), "+f"(d[62]), "+f"(d[63]), "+f"(d[64]), "+f"(d[65]), "+f"(d[66]), "+f"(d[67]), "+f"(d[68]), "+f"(d[69]), "+f"(d[70]), "+f"(d[71]), "+f"(d[72]), "+f"(d[73]), "+f"(d[74]), "+f"(d[75]), "+f"(d[76]), "+f"(d[77]), "+f"(d[78]), "+f"(d[79]), "+f"(d[80]), "+f"(d[81]), "+f"(d[82]), "+f"(d[83]), "+f"(d[84]), "+f"(d[85]), "+f"(d[86]), "+f"(d[87]), "+f"(d[88]), "+f"(d[89]), "+f"(d[90]), "+f"(d[91]), "+f"(d[92]), "+f"(d[93]), "+f"(d[94]), "+f"(d[95])
               : "r"(da), "r"(db), "n"(scale_d));
#undef R_
}
template <int scale_d> __device__ __forceinline__ void wgmma4_n128(float* d, uint32_t da, uint32_t db) {
#define R_ "{%0,%1,%2,%3,%4,%5,%6,%7,%8,%9,%10,%11,%12,%13,%14,%15,%16,%17,%18,%19,%20,%21,%22,%23,%24,%25,%26,%27,%28,%29,%30,%31,%32,%33,%34,%35,%36,%37,%38,%39,%40,%41,%42,%43,%44,%45,%46,%47,%48,%49,%50,%51,%52,%53,%54,%55,%56,%57,%58,%59,%60,%61,%62,%63}"
  asm volatile("{\n.reg .pred p, q;\n.reg .b64 a, b;\nsetp.ne.b32 p, %66, 0;\nsetp.eq.b32 q, 0, 0;\nmov.b64 a, {%64, 0x40000040};\nmov.b64 b, {%65, 0x40000040};\n"
               "wgmma.mma_async.sync.aligned.m64n128k16.f32.bf16.bf16 " R_ ", a, b, p, 1, 1, 0, 1;\nadd.s64 a, a, 2;\nadd.s64 b, b, 128;\n"
               "wgmma.mma_async.sync.aligned.m64n128k16.f32.bf16.bf16 " R_ ", a, b, q, 1, 1, 0, 1;\nadd.s64 a, a, 2;\nadd.s64 b, b, 128;\n"
               "wgmma.mma_async.sync.aligned.m64n128k16.f32.bf16.bf16 " R_ ", a, b, q, 1, 1, 0, 1;\nadd.s64 a, a, 2;\nadd.s64 b, b, 128;\n"
               "wgmma.mma_async.sync.aligned.m64n128k16.f32.bf16.bf16 " R_ ", a, b, q, 1, 1, 0, 1;\n}\n"
               : "+f"(d[0]), "+f"(d[1]), "+f"(d[2]), "+f"(d[3]), "+f"(d[4]), "+f"(d[5]), "+f"(d[6]), "+f"(d[7]), "+f"(d[8]), "+f"(d[9]), "+f"(d[10]), "+f"(d[11]), "+f"(d[12]), "+f"(d[13]), "+f"(d[14]), "+f"(d[15]), "+f"(d[16]), "+f"(d[17]), "+f"(d[18]), "+f"(d[19]), "+f"(d[20]), "+f"(d[21]), "+f"(d[22]), "+f"(d[23]), "+f"(d[24]), "+f"(d[25]), "+f"(d[26]), "+f"(d[27]), "+f"(d[28]), "+f"(d[29]), "+f"(d[30]), "+f"(d[31]), "+f"(d[32]), "+f"(d[33]), "+f"(d[34]), "+f"(d[35]), "+f"(d[36]), "+f"(d[37]), "+f"(d[38]), "+f"(d[39]), "+f"(d[40]), "+f"(d[41]), "+f"(d[42]), "+f"(d[43]), "+f"(d[44]), "+f"(d[45]), "+f"(d[46]), "+f"(d[47]), "+f"(d[48]), "+f"(d[49]), "+f"(d[50]), "+f"(d[51]), "+f"(d[52]), "+f"(d[53]), "+f"(d[54]), "+f"(d[55]), "+f"(d[56]), "+f"(d[57]), "+f"(d[58]), "+f"(d[59]), "+f"(d[60]), "+f"(d[61]), "+f"(d[62]), "+f"(d[63])
               : "r"(da), "r"(db), "n"(scale_d));
#undef R_
}
template <int scale_d> __device__ __forceinline__ void wgmma_n32(float* d, uint64_t descA, uint64_t descB) {
  asm volatile("{\n.reg .pred p;\nsetp.ne.b32 p, %18, 0;\n"
               "wgmma.mma_async.sync.aligned.m64n32k16.f32.bf16.bf16 {%0,%1,%2,%3,%4,%5,%6,%7,%8,%9,%10,%11,%12,%13,%14,%15}, %16, %17, p, 1, 1, 0, 1;\n}\n"
               : "+f"(d[0]), "+f"(d[1]), "+f"(d[2]), "+f"(d[3]), "+f"(d[4]), "+f"(d[5]), "+f"(d[6]), "+f"(d[7]), "+f"(d[8]), "+f"(d[9]), "+f"(d[10]), "+f"(d[11]), "+f"(d[12]), "+f"(d[13]), "+f"(d[14]), "+f"(d[15])
               : "l"(descA), "l"(descB), "n"(scale_d));
}
template <int scale_d, int tnsp_a> __device__ __forceinline__ void wgmma_n40(float* d, uint64_t descA, uint64_t descB) {
  asm volatile("{\n.reg .pred p;\nsetp.ne.b32 p, %22, 0;\n"
               "wgmma.mma_async.sync.aligned.m64n40k16.f32.bf16.bf16 {%0,%1,%2,%3,%4,%5,%6,%7,%8,%9,%10,%11,%12,%13,%14,%15,%16,%17,%18,%19}, %20, %21, p, 1, 1, %23, 1;\n}\n"
               : "+f"(d[0]), "+f"(d[1]), "+f"(d[2]), "+f"(d[3]), "+f"(d[4]), "+f"(d[5]), "+f"(d[6]), "+f"(d[7]), "+f"(d[8]), "+f"(d[9]), "+f"(d[10]), "+f"(d[11]), "+f"(d[12]), "+f"(d[13]), "+f"(d[14]), "+f"(d[15]), "+f"(d[16]), "+f"(d[17]), "+f"(d[18]), "+f"(d[19])
               : "l"(descA), "l"(descB), "n"(scale_d), "n"(tnsp_a));
}
template <int scale_d> __device__ __forceinline__ void wgmma_n40_rs(float* d, const uint32_t* a, uint64_t descB) {
  asm volatile("{\n.reg .pred p;\nsetp.ne.b32 p, %25, 0;\n"
               "wgmma.mma_async.sync.aligned.m64n40k16.f32.bf16.bf16 {%0,%1,%2,%3,%4,%5,%6,%7,%8,%9,%10,%11,%12,%13,%14,%15,%16,%17,%18,%19}, {%20,%21,%22,%23}, %24, p, 1, 1, 1;\n}\n"
               : "+f"(d[0]), "+f"(d[1]), "+f"(d[2]), "+f"(d[3]), "+f"(d[4]), "+f"(d[5]), "+f"(d[6]), "+f"(d[7]), "+f"(d[8]), "+f"(d[9]), "+f"(d[10]), "+f"(d[11]), "+f"(d[12]), "+f"(d[13]), "+f"(d[14]), "+f"(d[15]), "+f"(d[16]), "+f"(d[17]), "+f"(d[18]), "+f"(d[19])
               : "r"(a[0]), "r"(a[1]), "r"(a[2]), "r"(a[3]), "l"(descB), "n"(scale_d));
}
__device__ __forceinline__ uint64_t make_desc(uint32_t addr, uint32_t lbo_bytes, uint32_t sbo_bytes) {
  return (uint64_t)((addr & 0x3FFFF) >> 4) | ((uint64_t)(lbo_bytes >> 4) << 16) | ((uint64_t)(sbo_bytes >> 4) << 32) | (1ull << 62);
}

__device__ __forceinline__ void ldsm_x4(uint32_t addr, uint32_t& r0, uint32_t& r1, uint32_t& r2, uint32_t& r3) {
  asm volatile("ldmatrix.sync.aligned.m8n8.x4.shared.b16 {%0,%1,%2,%3}, [%4];" : "=r"(r0), "=r"(r1), "=r"(r2), "=r"(r3) : "r"(addr) : "memory");
}
__device__ __forceinline__ void ldsm_x4_t(uint32_t addr, uint32_t& r0, uint32_t& r1, uint32_t& r2, uint32_t& r3) {
  asm volatile("ldmatrix.sync.aligned.m8n8.x4.trans.shared.b16 {%0,%1,%2,%3}, [%4];" : "=r"(r0), "=r"(r1), "=r"(r2), "=r"(r3) : "r"(addr) : "memory");
}
__device__ __forceinline__ void stsm_x4(uint32_t addr, uint32_t r0, uint32_t r1, uint32_t r2, uint32_t r3) {
  asm volatile("stmatrix.sync.aligned.m8n8.x4.shared.b16 [%0], {%1,%2,%3,%4};" :: "r"(addr), "r"(r0), "r"(r1), "r"(r2), "r"(r3) : "memory");
}
__device__ __forceinline__ void sts128(uint32_t addr, uint32_t a, uint32_t b, uint32_t c, uint32_t d) {
  asm volatile("st.shared.v4.u32 [%0], {%1,%2,%3,%4};" :: "r"(addr), "r"(a), "r"(b), "r"(c), "r"(d) : "memory");
}
__device__ __forceinline__ float lds32f(uint32_t addr) {
  float v;
  asm volatile("ld.shared.f32 %0, [%1];" : "=f"(v) : "r"(addr) : "memory");
  return v;
}
__device__ __forceinline__ void sts32f(uint32_t addr, float a) {
  asm volatile("st.shared.f32 [%0], %1;" :: "r"(addr), "f"(a) : "memory");
}
__device__ __forceinline__ void mma_bf16(float (&c)[4], uint32_t a0, uint32_t a1, uint32_t a2, uint32_t a3, uint32_t b0, uint32_t b1) {
  asm volatile("mma.sync.aligned.m16n8k16.row.col.f32.bf16.bf16.f32 {%0,%1,%2,%3}, {%4,%5,%6,%7}, {%8,%9}, {%0,%1,%2,%3};"
               : "+f"(c[0]), "+f"(c[1]), "+f"(c[2]), "+f"(c[3]) : "r"(a0), "r"(a1), "r"(a2), "r"(a3), "r"(b0), "r"(b1));
}
__device__ __forceinline__ uint32_t pack_bf16(float lo, float hi) {
  uint32_t r;
  asm("cvt.rn.bf16x2.f32 %0, %1, %2;" : "=r"(r) : "f"(hi), "f"(lo));
  return r;
}
__device__ __forceinline__ float bf_lo(uint32_t v) { return __uint_as_float(v << 16); }
__device__ __forceinline__ float bf_hi(uint32_t v) { return __uint_as_float(v & 0xFFFF0000u); }
__device__ __forceinline__ void split3(float x, uint32_t& h, uint32_t& m, uint32_t& l) {
  h = pack_bf16(x, 0.f); x -= bf_lo(h);
  m = pack_bf16(x, 0.f); x -= bf_lo(m);
  l = pack_bf16(x, 0.f);
}
__device__ __forceinline__ float ex2(float x) { float r; asm("ex2.approx.ftz.f32 %0, %1;" : "=f"(r) : "f"(x)); return r; }
__device__ __forceinline__ float rcp_fast(float x) { float r; asm("rcp.approx.ftz.f32 %0, %1;" : "=f"(r) : "f"(x)); return r; }
__device__ __forceinline__ void red_v4(float* p, float a, float b, float c, float d) {
  asm volatile("red.global.add.v4.f32 [%0], {%1, %2, %3, %4};" :: "l"(p), "f"(a), "f"(b), "f"(c), "f"(d) : "memory");
}
__device__ __forceinline__ uint4 ld_ll(const uint4* p) {
  uint4 v;
  asm volatile("{\n.reg .b64 a, b;\nld.relaxed.gpu.global.v2.b64 {a, b}, [%4];\nmov.b64 {%0, %1}, a;\nmov.b64 {%2, %3}, b;\n}\n"
               : "=r"(v.x), "=r"(v.y), "=r"(v.z), "=r"(v.w) : "l"(p) : "memory");
  return v;
}
__device__ __forceinline__ void st_b64(uint2* p, uint32_t a, uint32_t b) {
  asm volatile("{\n.reg .b64 v;\nmov.b64 v, {%1, %2};\nst.relaxed.gpu.global.b64 [%0], v;\n}\n" :: "l"(p), "r"(a), "r"(b) : "memory");
}
__device__ __forceinline__ void st_b128(uint4* p, uint32_t a, uint32_t b, uint32_t c, uint32_t d) {
  asm volatile("{\n.reg .b128 v;\nmov.b128 v, {%1, %2, %3, %4};\nst.relaxed.gpu.global.b128 [%0], v;\n}\n" :: "l"(p), "r"(a), "r"(b), "r"(c), "r"(d) : "memory");
}
__device__ __forceinline__ uint4 ld_b128(const uint4* p) {
  uint4 v;
  asm volatile("{\n.reg .b128 v;\nld.relaxed.gpu.global.b128 v, [%4];\nmov.b128 {%0, %1, %2, %3}, v;\n}\n" : "=r"(v.x), "=r"(v.y), "=r"(v.z), "=r"(v.w) : "l"(p) : "memory");
  return v;
}

constexpr float LOG2E = 1.4426950408889634f;

struct Params {
  const __nv_bfloat16* x0;
  const __nv_bfloat16* wA_qkv;
  const __nv_bfloat16* wA_o;
  const __nv_bfloat16* wB_qkv;
  const __nv_bfloat16* wB_phi;
  const __nv_bfloat16* wB_o;
  __nv_bfloat16* out;
};

#define ACC_DEF(d, n) _Pragma("unroll") for (int i_ = 0; i_ < (n); i_++) asm volatile("" : "=f"(d[i_]))
#define ACC_FENCE(d, n) _Pragma("unroll") for (int i_ = 0; i_ < (n); i_++) asm volatile("" : "+f"(d[i_]) :: "memory")
#define PIN(a, n) _Pragma("unroll") for (int i_ = 0; i_ < (n); i_++) asm volatile("" : "+f"((a)[i_]))
#define PINU(a, n) _Pragma("unroll") for (int i_ = 0; i_ < (n); i_++) asm volatile("" : "+r"((a)[i_]))

#define STAGE64(acc, off, p0, KIND, SEND) { \
    uint32_t w_[4][4]; \
    _Pragma("unroll") for (int j_ = 0; j_ < 4; j_++) { \
      const int o_ = (off) + j_ * 8; \
      w_[j_][0] = pack_bf16(rs0 * acc[o_ + 0], rs0 * acc[o_ + 1]); \
      w_[j_][1] = pack_bf16(rs1 * acc[o_ + 2], rs1 * acc[o_ + 3]); \
      w_[j_][2] = pack_bf16(rs0 * acc[o_ + 4], rs0 * acc[o_ + 5]); \
      w_[j_][3] = pack_bf16(rs1 * acc[o_ + 6], rs1 * acc[o_ + 7]); \
    } \
    if ((SEND) && hsend) { \
      _Pragma("unroll") for (int j_ = 0; j_ < 4; j_++) { \
        w_[j_][0] = (w_[j_][0] & ~1u) | hbit; \
        st_b128(hbase + lane + ((KIND) * 4 + j_) * 32, w_[j_][0], w_[j_][1], w_[j_][2], w_[j_][3]); \
      } \
    } \
    _Pragma("unroll") for (int j_ = 0; j_ < 4; j_++) \
      stsm_x4((KIND) ? (p0) + (j_ >> 1) * 8192 + (srowoff >> 1) + ((((uint32_t)(j_ & 1) << 5) + lhi) ^ lsw2) \
                     : (p0) + srowoff + ((((uint32_t)j_ << 5) + lhi) ^ lsw), \
              w_[j_][0], w_[j_][1], w_[j_][2], w_[j_][3]); \
  }
#define RW(j) (((j) >> 1) * 4 + ((j) & 1))
__device__ __forceinline__ float rmax16(const float* p) {
  float m[4];
#pragma unroll
  for (int j = 0; j < 4; j++) m[j] = fmaxf(fmaxf(p[RW(j)], p[RW(j + 4)]), fmaxf(p[RW(j + 8)], p[RW(j + 12)]));
  const float r = fmaxf(fmaxf(m[0], m[1]), fmaxf(m[2], m[3]));
  return fmaxf(r, __shfl_xor_sync(0xffffffffu, r, 1));
}
__device__ __forceinline__ float rmin16(const float* p) {
  float m[4];
#pragma unroll
  for (int j = 0; j < 4; j++) m[j] = fminf(fminf(p[RW(j)], p[RW(j + 4)]), fminf(p[RW(j + 8)], p[RW(j + 12)]));
  const float r = fminf(fminf(m[0], m[1]), fminf(m[2], m[3]));
  return fminf(r, __shfl_xor_sync(0xffffffffu, r, 1));
}
__device__ __forceinline__ float exps16(float* o, const float* p, float c, float b) {
  float s[4];
#pragma unroll
  for (int j = 0; j < 16; j++) { o[j] = ex2(fmaf(p[RW(j)], c, b)); if (j < 4) s[j] = o[j]; else s[j & 3] += o[j]; }
  return (s[0] + s[1]) + (s[2] + s[3]);
}
__device__ __forceinline__ void store16(const float* e, float sum, uint32_t dst, uint32_t dsw, int c0) {
  const float inv = rcp_fast(sum + __shfl_xor_sync(0xffffffffu, sum, 1));
#pragma unroll
  for (int j = 0; j < 2; j++)
    sts128(dst + (((c0 + j) << 4) ^ dsw), pack_bf16(e[j * 8] * inv, e[j * 8 + 1] * inv), pack_bf16(e[j * 8 + 2] * inv, e[j * 8 + 3] * inv),
           pack_bf16(e[j * 8 + 4] * inv, e[j * 8 + 5] * inv), pack_bf16(e[j * 8 + 6] * inv, e[j * 8 + 7] * inv));
}
__device__ __forceinline__ void expp16(uint32_t* o, const float* p, float c0, float b0, float c1, float b1) {
#pragma unroll
  for (int j = 0; j < 8; j++) {
    const float c = (j & 1) ? c1 : c0, b = (j & 1) ? b1 : b0;
    o[j] = pack_bf16(ex2(fmaf(p[2 * j], c, b)), ex2(fmaf(p[2 * j + 1], c, b)));
  }
}
__device__ __forceinline__ void extrema(float* m, const float* p, float c0, float c1) {
#pragma unroll
  for (int i = 0; i < 4; i++) {
    const float* q = p + (i >> 1) * 16 + (i & 1) * 2;
    m[(i >> 1) * 4 + (i & 1)] = fminf(fminf(fminf(q[0], q[1]), fminf(q[4], q[5])), fminf(fminf(q[8], q[9]), fminf(q[12], q[13])));
    m[(i >> 1) * 4 + (i & 1) + 2] = fmaxf(fmaxf(fmaxf(q[0], q[1]), fmaxf(q[4], q[5])), fmaxf(fmaxf(q[8], q[9]), fmaxf(q[12], q[13])));
  }
#pragma unroll
  for (int o = 1; o <= 2; o <<= 1)
#pragma unroll
    for (int i = 0; i < 8; i++) { const float x = __shfl_xor_sync(0xffffffffu, m[i], o); m[i] = (i & 2) ? fmaxf(m[i], x) : fminf(m[i], x); }
#pragma unroll
  for (int i = 0; i < 8; i++) m[i] *= ((i & 2) ? -1.f : 1.f) * ((i & 1) ? c1 : c0);
}
#define SCHED_FENCE() asm volatile("pmevent 0;" ::: "memory")

__global__ void __cluster_dims__(2, 1, 1) __launch_bounds__(384, 1)
mega_kernel(const __grid_constant__ CUtensorMap tm_x0, const __grid_constant__ CUtensorMap tm_xo, const __grid_constant__ CUtensorMap tm_os,
            const __grid_constant__ CUtensorMap tm_o, const __grid_constant__ CUtensorMap tm_wf,
            const __grid_constant__ CUtensorMap tm_wqA, const __grid_constant__ CUtensorMap tm_wqB,
            const __grid_constant__ CUtensorMap tm_woA, const __grid_constant__ CUtensorMap tm_woB,
            const __grid_constant__ CUtensorMap tm_phi, const Params prm) {
  extern __shared__ __align__(1024) uint8_t smem_raw[];
  const uint32_t sbase = smem_u32(smem_raw);
  const uint32_t bar_full = sbase + OFF_BAR;
  const uint32_t bar_done = bar_full + 384;
  const uint32_t bar_stat = bar_full + 768, bar_stat2 = bar_full + 776, bar_epi = bar_full + 784, bar_phi = bar_full + 936  ;
  const uint32_t bar_xr = bar_full + 800, bar_lx = bar_full + 808, bar_kvf = bar_full + 816  , bar_stg = bar_full + 832;
  const uint32_t bar_chk = bar_full + 848;

  const int warp = __shfl_sync(0xffffffffu, threadIdx.x >> 5, 0), lane = threadIdx.x & 31;
  uint32_t rank;
  asm volatile("mov.u32 %0, %%cluster_ctarank;" : "=r"(rank));
  const int cta = (int)blockIdx.x - NAUX;
  const int cl = cta >> 1;
  const int jj = cl & 7, cc = cl >> 3;
  const int mm = cc * 2 + (int)rank;

#define LOAD_EPOCH() const unsigned epoch = ld_relaxed(&g_flags.epoch.v), ep1 = epoch + 1; (void)epoch
  int budget = 1 << 22;

  if (cta >= 0) {
    {
      const int tx = threadIdx.x;
      const __nv_bfloat16* pf = (tx < 128) ? prm.x0 + (size_t)(mm * 128 + tx) * D_MODEL + jj * 128
                                           : prm.wA_qkv + (size_t)(jj * 128 + (tx & 63)) * 3072 + ((tx - 128) >> 6) * 1024 + jj * 128 + rank * 64;
      if (tx < 320) asm volatile("prefetch.global.L2 [%0];" :: "l"(pf));
      else if (tx == 320) prefetch_tmap(&tm_x0);
      else if (tx == 352) prefetch_tmap(&tm_wqA);
      else if (tx == 383) asm volatile("prefetch.global.L2 [%0];" :: "l"(&g_flags.epoch.v));
    }
    if (elect_one()) {
#pragma unroll
      for (int i = 0; i < 4; i++) {
        const int u = warp * 4 + i;
        mbar_init(bar_full + u * 8, ((u >= 4 && u < 11) || (u > 32 && u != 40)) ? 2 : 1); mbar_init(bar_done + u * 8, 16);
      }
      mbar_init(bar_stat + warp * 16, 0x111111181182ull >> (4 * warp) & 15);
      mbar_init(bar_stat + warp * 16 + 8, 0x111111121811ull >> (4 * warp) & 15);
      mbar_init(bar_chk + 112 + (warp & 7) * 8, 1);
      asm volatile("fence.mbarrier_init.release.cluster;" ::: "memory");
    }
    __syncthreads();
    asm volatile("barrier.cluster.arrive.relaxed.aligned;" ::: "memory");
  }

  if (cta < 0) {
    LOAD_EPOCH();
    const uint32_t buf = sbase + warp * SLOT, bar = sbase + OFF_BAR + warp * 16;
    const uint32_t lsw = (lane & 7) << 4, lhi = (lane >> 4) << 4, lrow = (lane & 15) * 128;
    const bool el = elect_one();
    if (el) {
      mbar_init(bar, 1); mbar_init(bar + 8, 1);
      asm volatile("fence.mbarrier_init.release.cluster;" ::: "memory");
    }
#pragma unroll 1
    for (int rd = 0; rd < (NLAYERS > 1 ? 5 : 2); rd++) {
      if (rd >= 2 && warp >= 8) break;
      const int tk = rd < 2 ? blockIdx.x * 12 + warp : blockIdx.x * 8 + warp;
      const int half = tk & 1;
      const int blk = rd < 2 ? (tk >> 1) * 2 + rd : (4 - rd) * 16 + (tk >> 1);
      const CUtensorMap* tm = rd < 2 ? &tm_wqA : (rd == 2 ? &tm_wqB : &tm_wf);
      const int j0 = (blk & 15) >> 1;
#define AUX_LOAD(n) { const uint32_t d_ = buf + ((n) & 1) * 8192, b_ = bar + ((n) & 1) * 8; const int r_ = kslice(j0, 2 * (n) + half) * 64; \
        mbar_expect_tx(b_, 8192); tma_load_2d(d_, tm, b_, blk * 64, r_); tma_load_2d(d_ + 4096, tm, b_, blk * 64, r_ + 32); }
      if (el) {
        if (rd == 3) { wait_flag(&g_flags.wfready[j0].v, ep1 * 16); fence_proxy_async_global(); }
        AUX_LOAD(0); AUX_LOAD(1);
      }
      __syncwarp();
      float cs[8][4];
#pragma unroll
      for (int i = 0; i < 8; i++) cs[i][0] = cs[i][1] = cs[i][2] = cs[i][3] = 0.f;
#pragma unroll 1
      for (int n = 0; n < 8; n++) {
        const uint32_t tb = buf + (n & 1) * 8192 + lrow;
        mbar_wait(bar + (n & 1) * 8, (n >> 1) & 1);
#pragma unroll
        for (int i = 0; i < 16; i++) {
          uint32_t b0, b1, b2, b3;
          ldsm_x4_t(tb + (i >> 2) * 2048 + (((i & 3) * 32 + lhi) ^ lsw), b0, b1, b2, b3);
          mma_bf16(cs[2 * (i & 3)], 0x3F803F80u, 0x3F803F80u, 0x3F803F80u, 0x3F803F80u, b0, b1);
          mma_bf16(cs[2 * (i & 3) + 1], 0x3F803F80u, 0x3F803F80u, 0x3F803F80u, 0x3F803F80u, b2, b3);
        }
        __syncwarp();
        if (el && n < 6) AUX_LOAD(n + 2);
        __syncwarp();
      }
      if (lane < 4) {
#pragma unroll
        for (int i = 0; i < 8; i++) st_b64(&g_colsum[rd >= 2][blk * 32 + i * 4 + lane][half], __float_as_uint(cs[i][0]), (__float_as_uint(cs[i][1]) & ~3u) | (ep1 & 3));
      }
      __syncwarp();
    }
  } else if (warp >= 8) {
    asm volatile("setmaxnreg.dec.sync.aligned.u32 40;");
    if (warp == 8) {
      const bool el = elect_one();
      cluster_wait();
      if (el) {
#pragma unroll 1
        for (int l = 0; l < NLAYERS; l++) {
          const uint32_t par = l & 1;
          const CUtensorMap* tqk = par ? &tm_wf : &tm_wqA;
          const CUtensorMap* tv = par ? &tm_wqB : &tm_wqA;
          const CUtensorMap* two = par ? &tm_woB : &tm_woA;
          if (l == 1) { LOAD_EPOCH(); wait_flag(&g_flags.wfready[jj].v, ep1 * 16); fence_proxy_async_global(); }
#pragma unroll 1
          for (int u = 0; u < 32; u++) {
            if (u >= 4) mbar_wait_sl(bar_done + (u - 4) * 8, par);
            else if (l) mbar_wait_sl(bar_done + (43 + u + (u >> 1)) * 8, par ^ 1);
            else if (u == 1) __nanosleep(STAG1);
            else if (u == 2) mbar_wait_sl(bar_full, 0);
            const uint32_t fb = bar_full + u * 8;
            const bool res = u < 4 ? (l || u >= 2) : (u < 11 || (u >= 18 && u < 22));
            mbar_expect_tx(fb, res ? QST : QST + SLOT);
            const int row = kslice(jj, u < 4 ? u & 1 : (u < 18 ? u - 2 : (u < 22 ? u - 6 : u - 20))) * 64 + (int)rank * 32;
            const int ps = u < 4 ? u >> 1 : (u >= 18), col = jj * 128 + ps * 64;
            const int c0 = par ? jj * 128 + (ps ? 0 : 1024) : col;
            const uint32_t dst = sbase + (u & 3) * QST + rank * 4096;
            tma_load_2d_mc(dst, tqk, fb, c0, row);
            tma_load_2d_mc(dst + 8192, tqk, fb, c0 + (par ? 64 : 1024), row);
            tma_load_2d_mc(dst + 16384, tv, fb, col + 2048, row);
            if (l == 0 && u < 4) PROFT(473 + u);
          }
#pragma unroll 1
          for (int s = 0; s < 16; s++) {
            if (s < 5) { if (s != 2 && s != 4) mbar_wait_sl(bar_done + (28 + s) * 8, par); }
            else if (s != 14) mbar_wait_sl(bar_done + (27 + s - (s == 15)) * 8, par);
            const uint32_t fb = bar_full + (32 + s) * 8;
            mbar_expect_tx(fb, SLOT);
            tma_load_2d_mc(sbase + rank * 8192 + (uint32_t)((WO_BSLOT >> (4 * s)) & 15) * SLOT, two, fb, jj * 128 + (int)rank * 64, wslice(jj, s) * 64);
            const int ts = s + par;
            if (s >= 5 && ts < 8) {
              mbar_expect_tx(bar_chk + 104 + ts * 8, SLOT);
              tma_load_2d(sbase + (uint32_t)((WO_ASLOT(par) >> (4 * ts)) & 15) * SLOT, &tm_o, bar_chk + 104 + ts * 8, wslice(jj, ts) * 64, mm * 128);
            }
          }
        }
      }
      __syncwarp();
    } else if (warp == 9) {
      const bool el = elect_one();
      if (el) {
        PROFT(472);
        tma_load_2d(sbase + OFF_S, &tm_x0, bar_full, jj * 128, mm * 128);
        __nanosleep(STAG1);
        tma_load_2d(sbase + OFF_S + SLOT, &tm_x0, bar_full + 8, jj * 128 + 64, mm * 128);
      }
      __syncwarp();
      LOAD_EPOCH();
#pragma unroll 1
      for (int lp = 0; lp < 4 * NLAYERS; lp++) {
        const int l = lp >> 2, ph = lp & 3;
        if (ph == 3) continue;
        const uint32_t par = l & 1;
        const __nv_bfloat16* pb = g_obuf + (ph >> 1) * 64 + (size_t)(mm * 128 + (ph ? 0 : S_LEN) + (lane & 7) * 16 + (jj & 1) * 8) * D_MODEL + (jj >> 1) * 16;
        const CUtensorMap* tm = lp ? &tm_o : &tm_x0;
        const int row = mm * 128 + ((ph || !l) ? 0 : S_LEN);
        const uint32_t bit = ph ? O_BIT(l) : X_BIT(l - 1);
        const uint32_t slots = ph ? (uint32_t)(WO_ASLOT(par) >> (ph * 32 - 28)) : 0x8769876u;
        const unsigned long long fr = ph == 0 ? 0x06050400000000ull : ph == 1 ? (par ? 0x2120353535351Full : 0x22212035351F1Eull) : (par ? 0x27262524232232ull : 0x27262524233232ull);
        uint32_t rdy = (lp == 0 || (lp & 7) == 1) ? 0xFF : 0;
        mbar_wait_sl(ph ? bar_done + ((uint32_t)fr & 63) * 8 : (l ? bar_done + 47 * 8 : bar_full), ph ? par : (l ? par ^ 1 : 0));
#pragma unroll 1
        for (int i = 0; i < (ph == 1 ? 4 + par : 7); i++) {
          if (!((rdy >> i) & 1) && (i < NPOLL || ph == 1)) {
            const unsigned* pp = reinterpret_cast<const unsigned*>(pb + ((jj + i + 1 + ((lane >> 3) & (POLLW - 1))) & 7) * 128);
            if (i == 0) __nanosleep(POLL0);
            unsigned v0 = ld_relaxed(pp);
            __nanosleep(POLLGAP);
            unsigned v1 = ld_relaxed(pp);
            uint32_t no;
#pragma unroll 1
            for (int it = 0; it < (1 << 18); it++) {
              no = __ballot_sync(0xffffffffu, (v0 ^ bit) & 1);
              if (!(no & 0xFF)) break;
              v0 = ld_relaxed(pp);
              no = __ballot_sync(0xffffffffu, (v1 ^ bit) & 1);
              if (!(no & 0xFF)) break;
              v1 = ld_relaxed(pp);
            }
            rdy = ((1 | (no & 0xFF00 ? 0 : 2) | (no & 0xFF0000 ? 0 : 4) | (no >> 24 ? 0 : 8)) & ((1 << POLLW) - 1)) << i;
          }
          if (ph || i >= 4) mbar_wait_sl(bar_done + ((uint32_t)(fr >> (8 * i)) & 63) * 8, par);
          if (el) {
            if (i == 0) PROFT(320 + l * 16 + ph);
            const uint32_t cb = bar_chk + (ph & 1) * 112 + i * 8;
            mbar_expect_tx(cb, SLOT);
            tma_load_2d(sbase + ((slots >> (4 * i)) & 15) * SLOT, tm, cb, ((jj + i + 1) & 7) * 128 + (ph >> 1) * 64, row);
          }
          __syncwarp();
        }
        if (ph == 0 && el) {
          if (l) { wait_flag(&g_flags.xready[l][mm].v, ep1 * 8); fence_proxy_async_global(); }
#pragma unroll 1
          for (int u = 11; u < 34; u++) {
            if (u == 18) u = 22;
            mbar_wait_sl(bar_done + (u - 4) * 8, par);
            if (u == 32) mbar_expect_tx(bar_xr, 2 * SLOT);
            tma_load_2d(sbase + OFF_RA + (u & 3) * SLOT, tm, u < 32 ? bar_full + u * 8 : bar_xr, kslice(jj, u < 18 ? u - 2 : (u < 32 ? u - 20 : u - 32)) * 64, row);
            if (l == 0 && u < 16 && NLAYERS > 1) {
              if (u == 11) { mbar_expect_tx(bar_phi, SLOT + 8192); tma_load_2d(sbase + OFF_PHI, &tm_phi, bar_phi, 0, jj * 128); }
              else tma_load_2d(sbase + 12 * SLOT + (u - 12) * 4096, &tm_wqB, bar_phi, jj * 128 + ((u - 12) >> 1) * 64, mm * 64 + (u & 1) * 32);
            }
          }
        }
        __syncwarp();
      }
      cluster_wait();
    } else {
      const int hw = warp - 10;
      LOAD_EPOCH();
      const bool el = elect_one();
      cluster_wait();
      if (hw == 0) {
        mbar_wait_sl(bar_full + 8, 0);
        if (lane < 7) prefetch_tmap(lane == 0 ? &tm_os : lane == 1 ? &tm_o : lane == 2 ? &tm_wf : lane == 3 ? &tm_wqB : lane == 4 ? &tm_woA : lane == 5 ? &tm_woB : &tm_phi);
        if (lane < 4) asm volatile("prefetch.global.L2 [%0];" :: "l"(prm.wB_phi + jj * 4096 + mm * 256 + lane * 64));
#pragma unroll 1
        for (int i = 0; i < 8; i++) {
          asm volatile("prefetch.global.L2 [%0];" :: "l"(prm.wB_qkv + (size_t)(mm * 64 + (i & 3) * 16 + (lane >> 1)) * 3072 + (i >> 2) * 1024 + jj * 128 + (lane & 1) * 64));
          __nanosleep(PFGAP);
        }
      } else {
#pragma unroll 1
        for (int b = 0; b < 2; b++) {
          float4* z = reinterpret_cast<float4*>(g_kv[b] + (jj * 4) * KVH + mm * (4 * KVH / 16)) + lane;
#pragma unroll
          for (int i = 0; i < 5; i++) z[i * 32] = make_float4(0.f, 0.f, 0.f, 0.f);
        }
#pragma unroll 1
        for (int i = 0; i < 16; i++) {
          const int b = i >> 2;
          const uint32_t v = (b == 0 ? O_BIT(0) : b == 1 ? X_BIT(0) : (NLAYERS > 2 ? 1u : ep1)) + 1;
          uint4* p = b < 2 ? reinterpret_cast<uint4*>(g_obuf + (size_t)(b * S_LEN + mm * 128 + (i & 3) * 32 + (lane >> 3) * 8) * D_MODEL + jj * 128 + (b ? 0 : 64)) + (lane & 7)
                           : g_halo + (size_t)(mm * 8 + jj) * 512 + (i - 8) * 32 + 256 + lane;
          *p = make_uint4(v, v, v, v);
        }
        fence_proxy_async_global();
      }
      __syncwarp();
      uint32_t chkp = 0;
#pragma unroll 1
      for (int lp = 0; lp < 4 * NLAYERS; lp++) {
        const int l = lp >> 2, ph = lp & 3;
        if (ph >= 2 + hw) continue;
        const uint32_t par = l & 1;
        int lane; asm volatile("mov.u32 %0, %%laneid;" : "=r"(lane));
        if (hw) {
          const uint32_t bit = ph ? O_BIT(l) : X_BIT(l - 1);
          const uint32_t slots = ph ? (uint32_t)(WO_ASLOT(par) >> (ph * 32 - 28)) : 0x8769876u;
#pragma unroll 1
          for (int c = 0; c < 7; c++) {
            const uint32_t tile = sbase + ((slots >> (4 * c)) & 15) * SLOT;
            const int cb = c + (ph & 1) * 14;
#pragma unroll 1
            for (int it = 0; it < (1 << 12); it++) {
              mbar_wait_sl(bar_chk + cb * 8, (chkp >> cb) & 1);
              chkp ^= 1u << cb;
              if (el && c == 0) PROFT(ph == 1 ? 480 + l * 2 : 488 + l * 2 + (ph >> 1));
              if (lp == 0) break;
              uint32_t a1 = 1, o1 = 0;
#pragma unroll
              for (int i = 0; i < 16; i++) {
                uint32_t w;
                asm volatile("ld.shared.u32 %0, [%1];" : "=r"(w) : "r"(tile + i * 1024 + (lane & 7) * 132 + (lane >> 3) * 32) : "memory");
                a1 &= w; o1 |= w;
              }
              if (__all_sync(0xffffffffu, ((bit ? a1 : ~o1) & 1) != 0)) break;
              if (el) {
                fence_proxy_async_smem();
                mbar_expect_tx(bar_chk + cb * 8, SLOT);
                tma_load_2d(tile, &tm_o, bar_chk + cb * 8, ((jj + c + 1) & 7) * 128 + (ph >> 1) * 64, mm * 128 + (ph ? 0 : S_LEN));
                RETRY_COUNT();
              }
              __syncwarp();
            }
            if (el) mbar_arrive_local(bar_full + (c + (ph ? 25 + ph * 8 : 4)) * 8);
            __syncwarp();
          }
          if (ph) continue;
#pragma unroll 1
          for (int hp = 0; hp < 2; hp++) {
            const uint4* src = reinterpret_cast<const uint4*>(g_colsum[par][jj * 64 + hp * 32 + lane]);
            uint32_t bad;
            int it = 0;
            float c[6];
            do {
              bad = 0;
#pragma unroll
              for (int p = 0; p < 3; p++) {
                const uint4 v = ld_ll(src + ((par && p < 2) ? (hp ? -32 : 512) + p * 32 : p * 512));
                bad |= (v.y ^ ep1) | (v.w ^ ep1);
                c[2 * p] = __uint_as_float(v.x) + __uint_as_float(v.z); c[2 * p + 1] = __uint_as_float(v.y) + __uint_as_float(v.w);
              }
              bad &= 3;
              if (bad) __nanosleep(300);
            } while (bad && ++it < (1 << 16));
#pragma unroll
            for (int p = 0; p < 6; p++) {
              uint32_t h, m, lo;
              split3(c[p], h, m, lo);
              sts128(sbase + OFF_LNB + hp * 4096 + (p >> 1) * 1024 + lane * 32 + (p & 1) * 16, h | (m << 16), h | (lo << 16), h | (m << 16), lo | (m << 16));
            }
            fence_proxy_async_smem();
            __syncwarp();
            if (el) { mbar_arrive_local(hp ? bar_stat2 : bar_stat); if (hp == 0) PROFT(324 + l * 16); }
            __syncwarp();
          }
          continue;
        } else if (ph == 0) {
          mbar_wait_sl(bar_done + 24, par);
          const uint4* sp = reinterpret_cast<const uint4*>(g_stats + (size_t)(mm * 128) * 8) + lane;
#pragma unroll 1
          for (int hf = 0; hf < 4; hf++) {
            uint4 v[4];
            uint32_t bad;
            int it = 0;
            do {
              bad = 0;
#pragma unroll
              for (int i = 0; i < 4; i++) { v[i] = ld_ll(sp + (hf * 4 + i) * 32); bad |= (v[i].y ^ STAT_TAG(l)) | (v[i].w ^ STAT_TAG(l)); }
              bad &= 3;
              if (bad) __nanosleep(200);
            } while (bad && ++it < (1 << 16));
            __syncwarp();
            float mean = 0.f, m2 = 0.f;
#pragma unroll
            for (int i = 0; i < 4; i++) {
              float a = __uint_as_float(v[i].x) + __uint_as_float(v[i].z);
              a += __shfl_xor_sync(0xffffffffu, a, 1); a += __shfl_xor_sync(0xffffffffu, a, 2);
              a *= 0.125f;
              const float e0 = __uint_as_float(v[i].x) - a, e1 = __uint_as_float(v[i].z) - a;
              float q = fmaf(fmaf(e0, e0, e1 * e1), 128.f, __uint_as_float(v[i].y) + __uint_as_float(v[i].w));
              q += __shfl_xor_sync(0xffffffffu, q, 1); q += __shfl_xor_sync(0xffffffffu, q, 2);
              if ((lane & 3) == i) { mean = a; m2 = q; }
            }
            const uint32_t row = hf * 32 + (lane & 3) * 8 + (lane >> 2);
            uint32_t h, m, lo;
            split3(-0.5f * mean, h, m, lo);
            sts128(sbase + OFF_LNA + row * 16, h | (h << 16), m | (h << 16), lo | (m << 16), m | (lo << 16));
            sts32f(sbase + OFF_ST + row * 4, rsqrtf(m2 * (1.f / 1024.f) + 1e-5f));
          }
          fence_proxy_async_smem();
          __syncwarp();
          if (el) { mbar_arrive_local(bar_stat); PROFT(323 + l * 16); }
          __syncwarp();
#pragma unroll 1
          for (int i = 0; i < 8 - 4 * l; i++) {
            asm volatile("prefetch.global.L2 [%0];" :: "l"(i < 4 ? (l ? prm.wB_o : prm.wA_o) + (size_t)cta * 8192 + i * 2048 + lane * 64
                                                                 : prm.wB_qkv + (size_t)(cta * 8 + (i - 4) * 2 + (lane >> 4)) * 3072 + 2048 + (lane & 15) * 64));
            __nanosleep(PFGAP);
          }
          continue;
        }
        {
          {
            if (l & 1)
#pragma unroll 1
            for (int h = 0; h < 2; h++) {
              asm volatile("bar.sync %0, 288;" :: "r"(BAR_KV + h) : "memory");
              __syncwarp();
              PROFT(331 + l * 16 + h);
              if (lane < 16) signal_release(&g_flags.kvready[(l & 2) + h][jj][lane].v);
              const unsigned* kf = &g_flags.kvready[(l & 2) + h][jj][mm].v;
              unsigned v0 = ld_relaxed(kf);
              __nanosleep(150);
              unsigned v1 = ld_relaxed(kf);
#pragma unroll 1
              for (int it = 0; it < (1 << 18); it++) {
                if (v0 == ep1 * 16) break;
                v0 = ld_relaxed(kf);
                if (v1 == ep1 * 16) break;
                v1 = ld_relaxed(kf);
              }
              fence_acquire();
              __syncwarp();
              if (h) mbar_wait_sl(bar_lx, 1);
              if (el) {
                PROFT(333 + l * 16 + h);
                fence_proxy_async_global();
                mbar_expect_tx(bar_kvf + h * 8, 2 * KVH * 4);
#pragma unroll 1
                for (int i = 0; i < 4; i++)
                  asm volatile("cp.async.bulk.shared::cluster.global.mbarrier::complete_tx::bytes [%0], [%1], %2, [%3];"
                               :: "r"(sbase + ((i & 1) ? OFF_PHI + h * 4096 + (i >> 1) * 2048 : 11 * SLOT + (i >> 1) * 8192)),
                                  "l"(g_kv[l >> 1] + (jj * 4 + h * 2 + (i >> 1)) * KVH + (i & 1) * 2048), "r"((i & 1) ? 2048 : 8192), "r"(bar_kvf + h * 8) : "memory");
              }
              __syncwarp();
            }
          }
#pragma unroll 1
          for (uint32_t ev = l == NLAYERS - 1 ? 0x8u : (l == 0 ? 0x83654u : 0x83u); ev != 8; ev >>= 4) {
            const int e = ev & 15;
            asm volatile("bar.sync %0, 288;" :: "r"((0xFECA987 >> (4 * e)) & 15) : "memory");
            if (el) {
              if (e < 4) {
                PROFT(325 + l * 16 + e);
                tma_store_2d(&tm_o, sbase + 11 * SLOT, jj * 128 + 64, mm * 128 + S_LEN);
              } else {
                if (e == 5) mbar_expect_tx(bar_phi + 8, SLOT);
#pragma unroll 1
                for (int i = 0; i < 4; i++) {
                  const uint32_t a = sbase + (e > 4 ? 10 : 12) * SLOT + i * 4096;
                  const int c0 = (e > 4 ? 1024 : 0) + jj * 128 + (i >> 1) * 64, c1 = mm * 64 + (i & 1) * 32;
                  if (e == 5) tma_load_2d(a, &tm_wqB, bar_phi + 8, c0, c1); else tma_store_2d(&tm_wf, a, c0, c1);
                }
                if (e != 5) {
                  asm volatile("cp.async.bulk.commit_group;\ncp.async.bulk.wait_group.read 0;" ::: "memory");
                  mbar_arrive_local(bar_phi + (e - 4) * 4);
                }
              }
              if ((0x48 >> e) & 1) {
                bulk_commit_wait();
                signal_release(e == 6 ? &g_flags.wfready[jj].v : &g_flags.xready[l + 1][mm].v);
              }
              if (e == 3) PROFT(330 + l * 16);
              if (e == 6) PROFT(335);
            }
            __syncwarp();
          }
        }
      }
    }
    cluster_sync();
  } else {
    asm volatile("setmaxnreg.inc.sync.aligned.u32 232;");
    LOAD_EPOCH();
    const int wg = warp >> 2;
    const int r0 = warp * 16;
    const uint32_t pK = sbase + OFF_S, pV = sbase + OFF_S + SLOT;
#define PMASKS(on, bit) const uint32_t pm0 = ((on) && t == (g & 3) && (g >> 2) == (g & 1)), pm1 = ((on) && t == (g & 3) && (g >> 2) != (g & 1)), pbit = (bit)
#define PBIT0(w) (((w) & ~pm0) | (pbit & pm0))
#define PBIT1(w) (((w) & ~pm1) | (pbit & pm1))
#define LANE_CONSTS() \
    int lane; asm volatile("mov.u32 %0, %%laneid;" : "=r"(lane)); \
    const int g = lane >> 2, t = lane & 3; \
    const uint32_t srowoff = (r0 + (lane & 15)) * 128, lsw = (lane & 7) << 4, lhi = (lane >> 4) << 4, lsw2 = (lane & 6) << 3; \
    (void)g; (void)t; (void)srowoff; (void)lsw; (void)lhi; (void)lsw2;
    uint32_t stgp = 0, peer;
    asm volatile("mapa.shared::cluster.u32 %0, %1, %2;" : "=r"(peer) : "r"(sbase), "r"(rank ^ 1));
    peer -= sbase;
    const uint32_t dA0 = (((sbase & 0x3FFFF) + wg * 8192) >> 4) | 0x10000u, dB0 = ((sbase & 0x3FFFF) >> 4) | 0x2000000u;
    cluster_wait();
#define DESC(lo, hi) ((uint64_t)(uint32_t)(lo) | ((uint64_t)(hi) << 32))
#define STG_ARRIVE() { __syncwarp(); if (elect_one()) mbar_arrive_local(bar_stg); }
#define STG_WAIT() { mbar_wait(bar_stg, stgp); stgp ^= 1; }
#define PROFS() do {} while (0)
#define REL(addr) { if (elect_one()) { mbar_arrive_local(addr); asm volatile("mbarrier.arrive.shared::cluster.b64 _, [%0];" :: "r"((addr) + peer) : "memory"); } }
#define QSTEP(ACC, DA, SC, PRE) { \
      const uint32_t da = (DA), db = dB0 + (ub & 0x18) * (QST >> 7); \
      mbar_wait(ub, par); \
      PRE; \
      wgmma_fence(); \
      wgmma4_n192<SC>(ACC, da, db); \
      wgmma_commit(); PROFS(); }
#define QREL() { wgmma_wait<1>(); REL(ub + 376); ub += 8; }
#define RA_CUR (dA0 + (OFF_RA >> 4) + (ub & 0x18) * (SLOT >> 7))
#define PUMP1() { QSTEP(S1, RA_CUR, 1, {}); QREL(); }
#define PUMP0() { PUMP1(); SCHED_FENCE(); }
#define PUMP() if (h == 0) PUMP1()
#define WSTEP() { \
      const uint32_t s4 = (ub - bar_full - 256) >> 1; \
      const uint32_t da = dA0 + (((uint32_t)(WO_ASLOT(par) >> s4) & 15) << 10), db = dB0 + (((uint32_t)(WO_BSLOT >> s4) & 15) << 10); \
      mbar_wait(ub, par); \
      wgmma_fence(); \
      wgmma4_n128<1>(S1, da, db); \
      wgmma_commit(); PROFS(); \
      wgmma_wait<1>(); \
      if (s4) REL(ub + 376); \
      ub += 8; }
#define PUMPS(n) { _Pragma("unroll 1") for (int i_ = 0; i_ < (n); i_++) PUMP1(); }
#define SITE(n) { if ((BMASK >> (n)) & 1) PUMP1(); SCHED_FENCE(); }
#define LNSTEP(ACC, hh) { wgmma_fence(); wgmma_n192<1, 0>(ACC, make_desc(sbase + OFF_LNA + wg * 1024, 0, 128) ^ (1ull << 62), make_desc(sbase + OFF_LNB + (hh) * 4096, 0, 128) ^ (1ull << 62)); }
#define DRAIN_A(ACC, PMP) { \
      LANE_CONSTS(); \
      STAGE64(ACC, 64, pV, 1, 1); \
      PMP; \
      STAGE64(ACC, 32, pK, 0, 1); \
      STG_ARRIVE(); \
      _Pragma("unroll") for (int i_ = 0; i_ < 16; i_++) qa[i_] = pack_bf16(ACC[2 * i_], ACC[2 * i_ + 1]); \
      PINU(qa, 16); }
#define DRAIN_B(ACC) { \
      LANE_CONSTS(); \
      STAGE64(ACC, 64, pV, 1, 0); \
      _Pragma("unroll") for (int i_ = 0; i_ < 64; i_++) st[i_] = ACC[i_]; \
      PIN(st, 64); }
#define WARP_STORE(tm, tile, col, row) { fence_proxy_async_smem(); __syncwarp(); \
      if (elect_one()) { tma_store_2d(tm, (tile) + r0 * 128, col, (row) + r0); asm volatile("cp.async.bulk.commit_group;" ::: "memory"); } __syncwarp(); }
#define PUBLISH_O() WARP_STORE(&tm_os, pO, jj * 128 + h * 64, mm * 128)
#define X_OUT(pc, on) { \
      PMASKS(on, X_BIT(l)); \
      _Pragma("unroll") for (int j = (pc) * 4; j < (pc) * 4 + 4; j++) \
        stsm_x4(pK + (pc) * SLOT + srowoff + ((((uint32_t)(j & 3) << 5) + lhi) ^ lsw), \
                PBIT0(pack_bf16(S1[j * 8 + 0], S1[j * 8 + 1])), PBIT0(pack_bf16(S1[j * 8 + 2], S1[j * 8 + 3])), \
                PBIT1(pack_bf16(S1[j * 8 + 4], S1[j * 8 + 5])), PBIT1(pack_bf16(S1[j * 8 + 6], S1[j * 8 + 7]))); }
#define REST_P1(SKEW, HOOK) { \
      mbar_wait(bar_stat2, par); \
      LNSTEP(S1, 1); \
      _Pragma("unroll 1") while (ub < bar_full + 256) { \
        if (ub == bar_full + 256 - 8 * (SKEW) && wg == 0) bar_sync<BAR_SKEW, 256>(); \
        QSTEP(S1, RA_CUR, 1, {}); \
        if (ub == bar_full + 248 && wg == 1) bar_arrive<BAR_SKEW, 256>(); \
        QREL(); \
      } \
      hbase += 256; \
      HOOK; \
      mbar_wait(bar_done + (31 - (SKEW)) * 8, par);        \
      wgmma_wait<0>(); \
      ACC_FENCE(S1, 96); \
      REL(bar_done + 31 * 8); \
      PROF(13); }
#define FOLD(tile, rd) { \
          LANE_CONSTS(); \
          float d[32]; \
          ACC_DEF(d, 32); \
          mbar_wait(bar_phi + (rd) * 8, 0); \
          wgmma_fence(); \
          _Pragma("unroll") for (int i = 0; i < 2; i++) { \
            const uint64_t da = make_desc((tile) + wg * 8192 + i * 64, 16, 1024); \
            const uint64_t db = make_desc(sbase + OFF_PHI + wg * 4096 + i * 2048, 16, 512) ^ (3ull << 62); \
            wgmma_n32<0>(d + i * 16, da, db); wgmma_n32<1>(d + i * 16, da + 2, db + 64); \
          } \
          wgmma_commit(); \
          PUMP0(); \
          ACC_FENCE(d, 32); \
          bar_wg(wg); \
          _Pragma("unroll") for (int i = 0; i < 4; i++) { \
            const float* x = d + (i & 1) * 8 + (i >> 1) * 2; \
            if (rd) sts128((tile) + wg * 8192 + ((warp & 3) * 16 + (i >> 1) * 8 + g) * 128 + (((2 * t + (i & 1)) ^ g) << 4), \
                           pack_bf16(x[0], x[1]), pack_bf16(x[4], x[5]), pack_bf16(x[16], x[17]), pack_bf16(x[20], x[21])); \
            else stsm_x4((tile) + srowoff + ((((uint32_t)i << 5) + lhi) ^ lsw), pack_bf16(d[i * 8], d[i * 8 + 1]), pack_bf16(d[i * 8 + 2], d[i * 8 + 3]), \
                         pack_bf16(d[i * 8 + 4], d[i * 8 + 5]), pack_bf16(d[i * 8 + 6], d[i * 8 + 7])); \
          } \
          fence_proxy_async_smem(); \
          bar_arrive<BAR_WF + 3 * (rd), 288>(); }
#define LOAD_X0(base) \
      _Pragma("unroll") for (int j = 0; j < 8; j++) { \
        uint32_t x0, x1, x2, x3; \
        ldsm_x4((base) + (j >> 2) * SLOT + srowoff + ((((uint32_t)(j & 3) << 5) + lhi) ^ lsw), x0, x1, x2, x3); \
        S1[j * 8 + 0] = bf_lo(x0); S1[j * 8 + 1] = bf_hi(x0); S1[j * 8 + 2] = bf_lo(x1); S1[j * 8 + 3] = bf_hi(x1); \
        S1[j * 8 + 4] = bf_lo(x2); S1[j * 8 + 5] = bf_hi(x2); S1[j * 8 + 6] = bf_lo(x3); S1[j * 8 + 7] = bf_hi(x3); \
      }
#define LOAD_X() { \
      wgmma_wait<0>(); \
      mbar_wait(bar_xr, par); \
      LOAD_X0(sbase + OFF_RA); \
      ACC_FENCE(S1, 64); \
      __syncwarp(); if (elect_one()) mbar_arrive_local(bar_lx); }

    float S1[96];
#pragma unroll
    for (int i = 0; i < 64; i++) S1[i] = 0.f;
#pragma unroll 1
    for (int l = 0; l < NLAYERS; l++) {
      const uint32_t par = l & 1;
      bar_wg(wg);
      PROF(0);
      uint32_t ub = bar_full;
      const bool hsend = (warp == 7) && (mm < 15);
      const uint32_t hbit = (NLAYERS > 2) ? (l == 0) : (ep1 & 1);
      float S0[96];
      {
        LANE_CONSTS();
        ACC_DEF(S0, 96);
        QSTEP(S0, dA0 + (OFF_S >> 4), 0, {});
        ub += 8;
        PROF(1);
        if (l == 0) { mbar_wait(ub, 0); LOAD_X0(pK); }
        else { X_OUT(1, false); fence_proxy_async_smem(); }
        SCHED_FENCE();
        {
          float a0 = S1[0], a1 = S1[2], b0 = S1[1], b1 = S1[3];
#pragma unroll
          for (int i = 4; i < 64; i += 4) { a0 += S1[i]; b0 += S1[i + 1]; a1 += S1[i + 2]; b1 += S1[i + 3]; }
          a0 += b0; a1 += b1;
          a0 += __shfl_xor_sync(0xffffffffu, a0, 1); a1 += __shfl_xor_sync(0xffffffffu, a1, 1);
          a0 += __shfl_xor_sync(0xffffffffu, a0, 2); a1 += __shfl_xor_sync(0xffffffffu, a1, 2);
          a0 *= (1.f / 128.f); a1 *= (1.f / 128.f);
          asm volatile("" : "+f"(a0), "+f"(a1));
          bar_wg(wg);
          QSTEP(S0, dA0 + ((OFF_S + SLOT) >> 4), 1, wgmma_wait<0>());
          REL(ub + 376); ub += 8;
          SCHED_FENCE();
          float q0 = 0.f, q1 = 0.f;
          b0 = 0.f; b1 = 0.f;
#pragma unroll
          for (int i = 0; i < 64; i += 4) {
            const float d0 = S1[i] - a0, d1 = S1[i + 1] - a0, d2 = S1[i + 2] - a1, d3 = S1[i + 3] - a1;
            q0 = fmaf(d0, d0, q0); b0 = fmaf(d1, d1, b0); q1 = fmaf(d2, d2, q1); b1 = fmaf(d3, d3, b1);
          }
          q0 += b0; q1 += b1;
          q0 += __shfl_xor_sync(0xffffffffu, q0, 1); q1 += __shfl_xor_sync(0xffffffffu, q1, 1);
          q0 += __shfl_xor_sync(0xffffffffu, q0, 2); q1 += __shfl_xor_sync(0xffffffffu, q1, 2);
          if (t < 2) st_b64(g_stats + (size_t)(mm * 128 + r0 + g + t * 8) * 8 + jj, __float_as_uint(t ? a1 : a0), (__float_as_uint(t ? q1 : q0) & ~3u) | STAT_TAG(l));
        }
        if (l) { asm volatile("cp.async.bulk.wait_group 0;" ::: "memory"); bar_arrive<BAR_O + 3, 288>(); }
        ACC_DEF(S1, 96);
        QSTEP(S1, dA0 + (OFF_S >> 4), 0, {});
        QREL();
        QSTEP(S1, dA0 + ((OFF_S + SLOT) >> 4), 1, {});
        QREL();
#pragma unroll 1
        for (int i = 0; i < 14; i++) {
          QSTEP(S0, RA_CUR, 1, {});
          if (i == 0) PROF(2);
          QREL();
        }
      }
      LANE_CONSTS();
      uint4* hbase = g_halo + (size_t)(mm * 8 + jj) * 512;
      mbar_wait(bar_stat, par);
      LNSTEP(S0, 0);
      wgmma_commit();
      const float rs0 = lds32f(sbase + OFF_ST + (r0 + g) * 4), rs1 = lds32f(sbase + OFF_ST + (r0 + g + 8) * 4);
      PUMP0();
      ACC_FENCE(S0, 96);
      PROF(3);
      if (!par) {
        constexpr uint32_t par = 0;
        uint32_t qa[16];
        DRAIN_A(S0, PUMP0());
#pragma unroll 1
        for (int h = 0; h < 2; h++) {
          const uint32_t pO = sbase + (h ? 3 : 12) * SLOT;
          PROF(4 + h * 12);
          const bool fold = (l == 0 && h == 0 && NLAYERS > 1);
          if (fold) FOLD(pO, 0) else if (h == 0) PUMPS(HPUMP1);
          LANE_CONSTS();
          uint4 hv[8];
#pragma unroll
          for (int i = 0; i < 8; i++) hv[i] = make_uint4(hbit, 0, 0, 0);
          const bool hrec = (warp == 0 && mm > 0);
          if (hrec) {
#pragma unroll
            for (int i = 0; i < 8; i++) hv[i] = ld_b128(hbase + lane - 8 * 512 + i * 32);
          }
          if (h) { LOAD_X(); _Pragma("unroll 1") for (int i_ = 0; i_ < AW0; i_++) WSTEP(); } else PUMPS(HPUMP2);
          const uint32_t halo = sbase + OFF_HALO;
          STG_WAIT();
          if (warp == 0) {
#pragma unroll 1
            for (int it = 0; it < (1 << 16); it++) {
              uint32_t bad = 0;
#pragma unroll
              for (int i = 0; i < 8; i++) bad |= hv[i].x ^ hbit;
              if (__all_sync(0xffffffffu, (bad & 1) == 0)) break;
#pragma unroll
              for (int i = 0; i < 8; i++) hv[i] = ld_b128(hbase + lane - 8 * 512 + i * 32);
            }
#pragma unroll
            for (int i = 0; i < 8; i++)
              stsm_x4(i < 4 ? halo + srowoff + ((((uint32_t)i << 5) + lhi) ^ lsw)
                            : halo + (srowoff >> 1) + (i >> 1) * 1024 + ((((uint32_t)(i & 1) << 5) + lhi) ^ lsw2), hv[i].x, hv[i].y, hv[i].z, hv[i].w);
            __syncwarp();
          }
          PROF(5 + h * 12);
          const uint32_t kb1 = pK + r0 * 128, vb1 = pV + r0 * 64;
          const uint32_t kb0 = r0 ? kb1 - 2048 : halo, vb0 = r0 ? vb1 - 1024 : halo + 2048;
          const uint32_t vhs = r0 ? 8192 : 1024;
          float s[2][4][4];
          {
            uint32_t kf[2][4][4];
#pragma unroll
            for (int i = 0; i < 8; i++) {
              const int hh = i >> 2, jb = i & 3;
              ldsm_x4(((jb < 2) ? kb0 : kb1) + ((jb & 1) * 8 + (lane & 7)) * 128 + ((hh * 64 + ((lane >> 3) << 4)) ^ lsw), kf[hh][jb][0], kf[hh][jb][1], kf[hh][jb][2], kf[hh][jb][3]);
              s[hh][jb][0] = s[hh][jb][1] = s[hh][jb][2] = s[hh][jb][3] = 0.f;
            }
#pragma unroll
            for (int ks = 0; ks < 2; ks++)
#pragma unroll
              for (int i = 0; i < 8; i++) {
                const int hh = i >> 2, jb = i & 3;
                mma_bf16(s[hh][jb], qa[hh * 8 + ks * 4], qa[hh * 8 + ks * 4 + 1], qa[hh * 8 + ks * 4 + 2], qa[hh * 8 + ks * 4 + 3], kf[hh][jb][ks * 2], kf[hh][jb][ks * 2 + 1]);
              }
          }
          PUMP();
          if (fold) bar_arrive<BAR_WF + 2, 288>();
          PROF(6 + h * 12);
          const bool e = g & 1, hb = (2 * t + (g & 1)) <= g;
          uint32_t vf[2][2][2][4];
#pragma unroll
          for (int i = 0; i < 8; i++) {
            const int hh = i >> 2, ks = (i >> 1) & 1, dp = i & 1;
            ldsm_x4_t((ks ? vb1 + hh * 8192 : vb0 + hh * vhs) + (lane & 15) * 64 + ((dp * 32 + lhi) ^ lsw2), vf[hh][ks][dp][0], vf[hh][ks][dp][1], vf[hh][ks][dp][2], vf[hh][ks][dp][3]);
          }
          float va[2][2], vb[2][2], mx[2][2];
#pragma unroll
          for (int hh = 0; hh < 2; hh++) {
            va[hh][0] = e ? s[hh][1][1] : s[hh][1][0];
            vb[hh][0] = hb ? (e ? s[hh][2][1] : s[hh][2][0]) : (e ? s[hh][0][1] : s[hh][0][0]);
            va[hh][1] = e ? s[hh][2][3] : s[hh][2][2];
            vb[hh][1] = hb ? (e ? s[hh][3][3] : s[hh][3][2]) : (e ? s[hh][1][3] : s[hh][1][2]);
          }
          if (warp == 0 && mm == 0) {
#pragma unroll
            for (int hh = 0; hh < 2; hh++) { va[hh][0] = -INFINITY; if (!hb) { vb[hh][0] = -INFINITY; vb[hh][1] = -INFINITY; } }
          }
#pragma unroll
          for (int i = 0; i < 4; i++) mx[i >> 1][i & 1] = fmaxf(va[i >> 1][i & 1], vb[i >> 1][i & 1]);
#pragma unroll
          for (int o = 1; o <= 2; o <<= 1)
#pragma unroll
            for (int i = 0; i < 4; i++) mx[i >> 1][i & 1] = fmaxf(mx[i >> 1][i & 1], __shfl_xor_sync(0xffffffffu, mx[i >> 1][i & 1], o));
          const float sc0 = rs0 * (0.17677669529663687f * LOG2E), sc1 = rs1 * (0.17677669529663687f * LOG2E);
#pragma unroll
          for (int i = 0; i < 4; i++) {
            const float sc = (i & 1) ? sc1 : sc0, m = mx[i >> 1][i & 1];
            va[i >> 1][i & 1] = ex2((va[i >> 1][i & 1] - m) * sc); vb[i >> 1][i & 1] = ex2((vb[i >> 1][i & 1] - m) * sc);
            mx[i >> 1][i & 1] = va[i >> 1][i & 1] + vb[i >> 1][i & 1];
          }
          if (h == 0 && ASITE) { PIN(&va[0][0], 4); PIN(&vb[0][0], 4); PIN(&mx[0][0], 4); PUMP1(); }
#pragma unroll
          for (int o = 1; o <= 2; o <<= 1)
#pragma unroll
            for (int i = 0; i < 4; i++) mx[i >> 1][i & 1] += __shfl_xor_sync(0xffffffffu, mx[i >> 1][i & 1], o);
          const uint32_t selA = e ? 0x1044 : 0x4410, selB = e ? 0x3244 : 0x4432, selL = hb ? 0x4444 : selB, selH = hb ? selB : 0x4444;
          float o[2][4][4];
          uint32_t pa[2][6];
#pragma unroll
          for (int hh = 0; hh < 2; hh++) {
            const float i0 = rcp_fast(mx[hh][0]), i1 = rcp_fast(mx[hh][1]);
            const uint32_t w0 = pack_bf16(va[hh][0] * i0, vb[hh][0] * i0), w1 = pack_bf16(va[hh][1] * i1, vb[hh][1] * i1);
            pa[hh][0] = __byte_perm(w0, 0, selL); pa[hh][1] = __byte_perm(w0, 0, selA); pa[hh][2] = __byte_perm(w1, 0, selL);
            pa[hh][3] = __byte_perm(w0, 0, selH); pa[hh][4] = __byte_perm(w1, 0, selA); pa[hh][5] = __byte_perm(w1, 0, selH);
#pragma unroll
            for (int dj = 0; dj < 4; dj++) { o[hh][dj][0] = o[hh][dj][1] = o[hh][dj][2] = o[hh][dj][3] = 0.f; }
          }
          PROF(7 + h * 12);
#pragma unroll
          for (int i = 0; i < 8; i++) mma_bf16(o[i >> 2][i & 3], pa[i >> 2][0], 0u, pa[i >> 2][1], pa[i >> 2][2], vf[i >> 2][0][(i >> 1) & 1][(i & 1) * 2], vf[i >> 2][0][(i >> 1) & 1][(i & 1) * 2 + 1]);
#pragma unroll
          for (int i = 0; i < 8; i++) mma_bf16(o[i >> 2][i & 3], pa[i >> 2][3], pa[i >> 2][4], 0u, pa[i >> 2][5], vf[i >> 2][1][(i >> 1) & 1][(i & 1) * 2], vf[i >> 2][1][(i >> 1) & 1][(i & 1) * 2 + 1]);
          if (h == 0) PUMP1() else mbar_wait(bar_done + 30 * 8, par);
          if (fold) mbar_wait(bar_phi, 1);
#pragma unroll
          for (int i = 0; i < 4; i++) {
            const int hh = i >> 1, dp = i & 1;
            PMASKS(true, O_BIT(l));
            stsm_x4(pO + srowoff + ((hh * 64 + dp * 32 + lhi) ^ lsw), PBIT0(pack_bf16(o[hh][dp * 2][0], o[hh][dp * 2][1])), PBIT0(pack_bf16(o[hh][dp * 2][2], o[hh][dp * 2][3])),
                    PBIT1(pack_bf16(o[hh][dp * 2 + 1][0], o[hh][dp * 2 + 1][1])), PBIT1(pack_bf16(o[hh][dp * 2 + 1][2], o[hh][dp * 2 + 1][3])));
          }
          PUBLISH_O();
          PROF(11 + h * 12);
          if (h) break;
          if (fold) { PUMPS(FPUMP); FOLD(pK, 1); }
          REST_P1(ASKEW, asm volatile("cp.async.bulk.wait_group.read 0;" ::: "memory"));
          if (fold) mbar_wait(bar_phi + 8, 1);
          DRAIN_A(S1, {});
        }
      } else {
        constexpr uint32_t par = 1;
        float st[64];
        DRAIN_B(S0);
        if (warp < 2) sts128(sbase + OFF_ONES + warp * 512 + lane * 16, 0x3F803F80u, 0x3F803F80u, 0x3F803F80u, 0x3F803F80u);
        const float c0 = rs0 * LOG2E, c1 = rs1 * LOG2E;
#define KV_MMA(vs) { \
          const uint32_t dp = dA0 + 12 * 1024 - wg * 2560, dv = dA0 + (vs) * 1024 + ((OFF_ONES - (vs) * SLOT - 16) << 12) - wg * (512 << 16); \
          STG_WAIT(); \
          wgmma_fence(); \
          _Pragma("unroll") for (int ks = 0; ks < 8; ks++) { \
            const uint64_t a = DESC(dp + ks * 128, 0x40000040), b = DESC(dv + ks * (64 - (64 << 16)), 0x80000020); \
            if (ks == 0) wgmma_n40<0, 1>(kv, a, b); else wgmma_n40<1, 1>(kv, a, b); } \
          wgmma_commit(); }
#define KV_RED(hp) { \
          float* kvg = g_kv[l >> 1] + (jj * 4 + (hp) * 2 + wg) * KVH + ((warp & 3) * 32 + lane) * 4; \
          _Pragma("unroll") for (int i = 0; i < 4; i++) red_v4(kvg + i * 512, kv[i * 4], kv[i * 4 + 1], kv[i * 4 + 2], kv[i * 4 + 3]); \
          if (t == 0) red_v4(kvg + 2048, kv[16], kv[17], kv[18], kv[19]); \
          bar_arrive<BAR_KV + (hp), 288>(); }
#define KV_TILE(hp) { \
          LANE_CONSTS(); \
          float4 v[5]; \
          mbar_wait(bar_kvf + (hp) * 8, l >> 1); \
          PROF(25 + (hp)); \
          _Pragma("unroll") for (int i = 0; i < 5; i++) \
            asm volatile("ld.shared.v4.f32 {%0, %1, %2, %3}, [%4];" : "=f"(v[i].x), "=f"(v[i].y), "=f"(v[i].z), "=f"(v[i].w) \
                         : "r"(i < 4 ? pV + wg * 8192 + i * 2048 + (warp & 3) * 512 + lane * 16 : sbase + OFF_PHI + (hp) * 4096 + warp * 512 + g * 64) : "memory"); \
          bar_wg(wg); \
          const uint32_t e = lane & 7, jt = ((lane >> 1) & 4) + (e >> 1); \
          const uint32_t row = ((((warp >> 1) ^ wg) & 1) << 5) + ((jt & 1) << 4) + ((warp & 1) << 3) + (jt & 6) + (e & 1); \
          const uint32_t kd = pV + wg * 8192 + row * 128, ksw = (row & 7) << 4; \
          _Pragma("unroll") for (int i = 0; i < 2; i++) { \
            const float4 a = v[i * 2], b = v[i * 2 + 1]; \
            stsm_x4(kd + ((i * 32 + lhi) ^ ksw), pack_bf16(a.x, a.y), pack_bf16(a.z, a.w), pack_bf16(b.x, b.y), pack_bf16(b.z, b.w)); \
          } \
          stsm_x4(kd + ((64u + lhi) ^ ksw), pack_bf16(v[4].x, 1.f), pack_bf16(v[4].z, 1.f), 0u, 0u); }
#pragma unroll 1
        for (int h = 0; h < 2; h++) {
          PROF(4 + h * 2);
          SITE(0);
          LANE_CONSTS();
          const uint32_t dsw = (uint32_t)(g ^ (2 * t)) << 4, dst = ((t & 2) ? pK : sbase + 12 * SLOT) + (r0 + g) * 128;
          float e[16], f[16];
          float mn0 = rmin16(st);
          asm volatile("" : "+f"(mn0)); SCHED_FENCE();
          float sa = exps16(e, st, -c0, mn0 * c0), mx0 = rmax16(st);
          asm volatile("" : "+f"(sa), "+f"(mx0)); PIN(e, 16); SITE(1);
          if (h) STG_WAIT();
          store16(e, sa, dst, dsw, 4);
          float sb = exps16(f, st, c0, -mx0 * c0), mn1 = rmin16(st + 2);
          asm volatile("" : "+f"(sb), "+f"(mn1)); PIN(f, 16); SITE(2);
          store16(f, sb, dst, dsw, 0);
          float sc = exps16(e, st + 2, -c1, mn1 * c1), mx1 = rmax16(st + 2);
          asm volatile("" : "+f"(sc), "+f"(mx1)); PIN(e, 16); SITE(3);
          store16(e, sc, dst + 1024, dsw, 4);
          float sd = exps16(f, st + 2, c1, -mx1 * c1);
          asm volatile("" : "+f"(sd)); PIN(f, 16); SITE(4);
          store16(f, sd, dst + 1024, dsw, 0);
          PROF(5 + h * 2);
          if (h) break;
          {
            float kv[20];
            ACC_DEF(kv, 20);
            fence_proxy_async_smem();
            STG_ARRIVE();
            KV_MMA(11);
            PUMP0();
            ACC_FENCE(kv, 20);
            KV_RED(0);
            STG_ARRIVE();
          }
#pragma unroll
          for (int i = 0; i < 32; i++) st[i] = st[32 + i];
        }
        float mq[8];
        {
          float kv[20];
          mbar_wait(bar_stat2, par);
          LNSTEP(S1, 1);
          ub = bar_full + 240;
          PUMP1();
          if (wg == 0) bar_sync<BAR_SKEW, 256>();
          QSTEP(S1, RA_CUR, 1, {});
          if (wg == 1) bar_arrive<BAR_SKEW, 256>();
          QREL();
          if (KT0) KV_TILE(0);
          mbar_wait(bar_done + 30 * 8, par);
          wgmma_wait<0>();
          ACC_FENCE(S1, 96);
          if (!(RLATE & 2)) REL(bar_done + 31 * 8);
          PROF(13);
          LANE_CONSTS();
          STAGE64(S1, 64, sbase + 3 * SLOT, 1, 0);
          fence_proxy_async_smem();
          STG_ARRIVE();
          if (RLATE & 2) REL(bar_done + 31 * 8);
#pragma unroll
          for (int i = 0; i < 32; i++) st[i] = S1[i];
          PIN(st, 32);
          PROF(16);
          ACC_DEF(kv, 20);
          KV_MMA(3);
          SCHED_FENCE();
          extrema(mq, st, c0, c1);
          PIN(mq, 8);
          SCHED_FENCE();
          wgmma_wait<0>();
          ACC_FENCE(kv, 20);
          KV_RED(1);
          PROF(17);
        }
#pragma unroll 1
        for (int h = 0; h < 2; h++) {
          const uint32_t pO = sbase + (h ? 3 : 8) * SLOT;
          LANE_CONSTS();
          uint32_t fq[32];
          expp16(fq, st, -c0, mq[0], -c1, mq[1]); expp16(fq + 8, st, c0, mq[2], c1, mq[3]); PINU(fq, 16);
          PROF(18 + h * 14);
          if (h) {
            asm volatile("cp.async.bulk.wait_group.read 0;" ::: "memory");
            uint32_t n;
#pragma unroll 1
            while (ub < bar_full + 8 * FILL) {
              int it = 0;
              do {
                asm volatile("{\n.reg .pred p, q;\nsetp.ne.u32 q, %4, 0;\nmbarrier.test_wait.parity.shared::cta.b64 p, [%1], %2;\nand.pred p, p, q;\n"
                             "barrier.red.popc.aligned.u32 %0, %3, 128, p;\n}\n"
                             : "=r"(n) : "r"((warp & 3) ? ub : bar_kvf + 8), "r"((warp & 3) ? par : l >> 1), "r"(2 + wg), "r"((warp & 3) | (uint32_t)(lane == 0)) : "memory");
                n = __shfl_sync(0xffffffffu, n, 0);
              } while (n == 0 && ++it < (1 << 20));
              if (n & 1) break;
              WSTEP();
            }
          }
          if (h || !KT0) {
            KV_TILE(h);
            fence_proxy_async_smem();
            STG_ARRIVE();
          }
          SCHED_FENCE();
          expp16(fq + 16, st + 16, -c0, mq[4], -c1, mq[5]); PINU(fq + 16, 8);
          if (h || !KT0) STG_WAIT();
          wgmma_wait<0>();
          ACC_FENCE(S1, 64);
          PROF(19 + h * 14);
          float o[4][20];
#define O_MMA(hh) { \
            const uint64_t db = make_desc(pV + (hh) * 8192, 16, 1024); \
            ACC_DEF(o[(hh) * 2], 20); ACC_DEF(o[(hh) * 2 + 1], 20); \
            wgmma_fence(); \
            wgmma_n40_rs<0>(o[(hh) * 2], fq + (hh) * 16, db + 256); wgmma_n40_rs<0>(o[(hh) * 2 + 1], fq + (hh) * 16 + 8, db); \
            wgmma_n40_rs<1>(o[(hh) * 2], fq + (hh) * 16 + 4, db + 384); wgmma_n40_rs<1>(o[(hh) * 2 + 1], fq + (hh) * 16 + 12, db + 128); \
            wgmma_commit(); }
          O_MMA(0);
          SCHED_FENCE();
          expp16(fq + 24, st + 16, c0, mq[6], c1, mq[7]); PINU(fq + 24, 8);
          SCHED_FENCE();
          PMASKS(true, O_BIT(l));
#pragma unroll
          for (int hh = 0; hh < 2; hh++) {
            if (hh && !OW) O_MMA(1);
            wgmma_wait<0>();
            ACC_FENCE(o[hh * 2], 20); ACC_FENCE(o[hh * 2 + 1], 20);
            if (!hh && OW) { O_MMA(1); SCHED_FENCE(); }
            const float* x = o[hh * 2];
            const float* y = o[hh * 2 + 1];
            const float rx0 = rcp_fast(x[17]), ry0 = rcp_fast(y[17]), rx1 = rcp_fast(x[19]), ry1 = rcp_fast(y[19]);
            const float i0 = rcp_fast(fmaf(x[16], rx0, y[16] * ry0) + 1e-6f), i1 = rcp_fast(fmaf(x[18], rx1, y[18] * ry1) + 1e-6f);
            const float ax0 = rx0 * i0, ay0 = ry0 * i0, ax1 = rx1 * i1, ay1 = ry1 * i1;
#pragma unroll
            for (int dp = 0; dp < 2; dp++)
              stsm_x4(pO + srowoff + ((hh * 64 + dp * 32 + lhi) ^ lsw),
                      PBIT0(pack_bf16(fmaf(x[dp * 8], ax0, y[dp * 8] * ay0), fmaf(x[dp * 8 + 1], ax0, y[dp * 8 + 1] * ay0))),
                      PBIT0(pack_bf16(fmaf(x[dp * 8 + 2], ax1, y[dp * 8 + 2] * ay1), fmaf(x[dp * 8 + 3], ax1, y[dp * 8 + 3] * ay1))),
                      PBIT1(pack_bf16(fmaf(x[dp * 8 + 4], ax0, y[dp * 8 + 4] * ay0), fmaf(x[dp * 8 + 5], ax0, y[dp * 8 + 5] * ay0))),
                      PBIT1(pack_bf16(fmaf(x[dp * 8 + 6], ax1, y[dp * 8 + 6] * ay1), fmaf(x[dp * 8 + 7], ax1, y[dp * 8 + 7] * ay1))));
          }
          PUBLISH_O();
          PROF(20 + h * 14);
          if (h) break;
#pragma unroll
          for (int i = 0; i < 32; i++) st[i] = S1[32 + i];
          PIN(st, 32);
          LOAD_X();
          bar_wg(wg);
          WSTEP();
          SCHED_FENCE();
          extrema(mq, st, c0, c1);
          PIN(mq, 8);
          PROF(31);
        }
      }
      __syncwarp();
      if (elect_one()) mbar_arrive_local(bar_epi);
      bar_wg(wg);
#pragma unroll 1
      while (ub < bar_full + 384) {
        WSTEP();
        if (ub == bar_full + 8 * 41) { asm volatile("cp.async.bulk.wait_group.read 0;" ::: "memory"); PROF(35); }
        if (ub == bar_full + 8 * 42) PROF(36);
      }
      wgmma_wait<0>();
      ACC_FENCE(S1, 64);
      if (!RLATE) REL(bar_done + 47 * 8);
      PROF(37);
      {
        LANE_CONSTS();
        X_OUT(0, l < NLAYERS - 1);
        WARP_STORE(l < NLAYERS - 1 ? &tm_os : &tm_xo, pK, jj * 128, mm * 128 + (l < NLAYERS - 1 ? S_LEN : 0));
        if (RLATE) REL(bar_done + 47 * 8);
        if (l == NLAYERS - 1) {
          X_OUT(1, false);
          WARP_STORE(&tm_xo, pV, jj * 128 + 64, mm * 128);
          asm volatile("cp.async.bulk.wait_group 0;" ::: "memory");
        }
      }
#pragma unroll
      for (int i = 32; i < 64; i++) { uint32_t c; asm volatile("mov.b32 %0, %1;" : "=r"(c) : "f"(S1[i])); S1[i] = __uint_as_float(c); }
      PROF(38);
    }
    const int tid = threadIdx.x;
    if (tid == 0) {
      unsigned old = atomicAdd(&g_flags.done.v, 1);
      if (old == ep1 * NMAIN - 1) {
        asm volatile("st.relaxed.gpu.global.u32 [%0], %1;" :: "l"(&g_flags.epoch.v), "r"(ep1) : "memory");
      }
    }
    __syncwarp();
    cluster_sync();
  }
}

typedef CUresult (*PFN_encode)(CUtensorMap*, CUtensorMapDataType, cuuint32_t, void*, const cuuint64_t*, const cuuint64_t*,
                               const cuuint32_t*, const cuuint32_t*, CUtensorMapInterleave, CUtensorMapSwizzle,
                               CUtensorMapL2promotion, CUtensorMapFloatOOBfill);

CUtensorMap make_map(PFN_encode enc, const void* ptr, uint64_t inner, uint64_t outer, uint32_t box_inner, uint32_t box_outer,
                     CUtensorMapSwizzle swz = CU_TENSOR_MAP_SWIZZLE_128B) {
  CUtensorMap m;
  cuuint64_t dims[2] = {inner, outer};
  cuuint64_t strides[1] = {inner * 2};
  cuuint32_t box[2] = {box_inner, box_outer};
  cuuint32_t es[2] = {1, 1};
  enc(&m, CU_TENSOR_MAP_DATA_TYPE_BFLOAT16, 2, const_cast<void*>(ptr), dims, strides, box, es, CU_TENSOR_MAP_INTERLEAVE_NONE,
      swz, CU_TENSOR_MAP_L2_PROMOTION_L2_256B, CU_TENSOR_MAP_FLOAT_OOB_FILL_NONE);
  return m;
}

}

extern "C" void kernel_launch(void* const* d_in, const int* in_sizes, int n_in, void* d_out, int out_size) {
  (void)in_sizes; (void)n_in; (void)out_size;
  static PFN_encode enc = nullptr;
  if (!enc) {
    void* fn = nullptr;
    cudaDriverEntryPointQueryResult qr;
    cudaGetDriverEntryPoint("cuTensorMapEncodeTiled", &fn, cudaEnableDefault, &qr);
    enc = (PFN_encode)fn;
    cudaFuncSetAttribute(mega_kernel, cudaFuncAttributeMaxDynamicSharedMemorySize, SMEM_BYTES);
  }
  Params prm;
  prm.x0 = (const __nv_bfloat16*)d_in[0];
  prm.wA_qkv = (const __nv_bfloat16*)d_in[1];
  prm.wA_o = (const __nv_bfloat16*)d_in[2];
  prm.wB_qkv = (const __nv_bfloat16*)d_in[4];
  prm.wB_phi = (const __nv_bfloat16*)d_in[5];
  prm.wB_o = (const __nv_bfloat16*)d_in[6];
  prm.out = (__nv_bfloat16*)d_out;
  void *obuf = nullptr, *wf = nullptr;
  cudaGetSymbolAddress(&obuf, g_obuf);
  cudaGetSymbolAddress(&wf, g_wfold);
  CUtensorMap tm_x0 = make_map(enc, d_in[0], D_MODEL, S_LEN, 64, 128);
  CUtensorMap tm_xo = make_map(enc, d_out, D_MODEL, S_LEN, 64, 16);
  CUtensorMap tm_os = make_map(enc, obuf, D_MODEL, 2 * S_LEN, 64, 16);
  CUtensorMap tm_o = make_map(enc, obuf, D_MODEL, 2 * S_LEN, 64, 128);
  CUtensorMap tm_wf = make_map(enc, wf, 2048, D_MODEL, 64, 32);
  CUtensorMap tm_wqA = make_map(enc, d_in[1], 3 * D_MODEL, D_MODEL, 64, 32);
  CUtensorMap tm_wqB = make_map(enc, prm.wB_qkv, 3 * D_MODEL, D_MODEL, 64, 32);
  CUtensorMap tm_woA = make_map(enc, prm.wA_o, D_MODEL, D_MODEL, 64, 64);
  CUtensorMap tm_woB = make_map(enc, prm.wB_o, D_MODEL, D_MODEL, 64, 64);
  CUtensorMap tm_phi = make_map(enc, prm.wB_phi, 32, 1024, 32, 128, CU_TENSOR_MAP_SWIZZLE_64B);
  mega_kernel<<<NMAIN + NAUX, 384, SMEM_BYTES>>>(tm_x0, tm_xo, tm_os, tm_o, tm_wf, tm_wqA, tm_wqB, tm_woA, tm_woB, tm_phi, prm);
}
```

```cpp
#include <cuda_runtime.h>
#include <cuda.h>
#include <cuda_bf16.h>
#include <stdint.h>

#define NLAYERS 4

#define STAG1 300
#define HPUMP1 2
#define HPUMP2 2
#define ASKEW 2
#define FPUMP 2
#define PFGAP 100
#define POLLW 4
#define POLL0 0
#define POLLGAP 120
#define OW 1
#define KT0 0
#define NPOLL 4
#define AW0 0
#define RLATE 0
#define FSTART 0
#define MAPV 1
#define ORD 15
#define FILL 40
#define BMASK 0x1F
#define ASITE 1
namespace {

constexpr int S_LEN = 2048, D_MODEL = 1024;
constexpr int NAUX = 4, NMAIN = 128;
constexpr int SLOT = 16384;
constexpr int QST = 24576;
constexpr int OFF_RA = 6 * SLOT, OFF_S = 10 * SLOT;
constexpr int OFF_HALO = 13 * SLOT, OFF_LNB = OFF_HALO  , OFF_ONES = OFF_HALO + 3072;
constexpr int OFF_ST = OFF_HALO + 7168  , OFF_PHI = OFF_HALO + 8192;
constexpr int OFF_BAR = 14 * SLOT;
constexpr int OFF_LNA = OFF_BAR + 1024;
constexpr int SMEM_BYTES = OFF_LNA + 2048;
#define WO_ASLOT(par) ((par) ? 0x9876CAB39876CA98ull : 0x98C76BA398C7698Cull)
constexpr unsigned long long WO_BSLOT = 0x5432105421054210ull;
__device__ __forceinline__ int srcb(int j, int i, int ph) { return ((ORD >> ph) & 1) ? (i + (i >= j)) & 7 : (j + i + 1) & 7; }
__device__ __forceinline__ int kslice(int j, int i) { return i < 2 ? 2 * j + i : (i < 9 ? 2 * srcb(j, i - 2, 0) : 2 * srcb(j, i - 9, 3) + 1); }
__device__ __forceinline__ int wslice(int j, int s) { return 2 * ((s & 7) ? srcb(j, (s & 7) - 1, 1 + (s >> 3)) : j) + (s >> 3); }
constexpr int KVH = 5 * 128 * 4;

struct __align__(128) Flag { unsigned v; unsigned pad[31]; };
struct Flags {
  Flag xready[4][16];
  Flag kvready[4][8][16];
  Flag wfready[8];
  Flag done;
  Flag epoch;
};

__device__ Flags g_flags;
__device__ __nv_bfloat16 g_obuf[2 * S_LEN * D_MODEL];
#define O_BIT(l) ((epoch * NLAYERS + (l) + 1) & 1u)
#define X_BIT(l) ((epoch * (NLAYERS - 1) + (l) + 1) & 1u)
__device__ __nv_bfloat16 g_wfold[D_MODEL * 2048];
__device__ uint4 g_halo[16 * 8 * 512];
__device__ float g_kv[2][32 * KVH];
__device__ __align__(128) uint2 g_colsum[2][1536][2];
__device__ __align__(128) uint2 g_stats[S_LEN * 8];
#define STAT_TAG(l) ((ep1 * NLAYERS + (l) + 1) & 3u)

#define RETRY_COUNT()
#define PROFL 1
#define PROFW 0
#define KVFLAG 1
#define PROFT(i) do {} while (0)
#define PROF(i) do {} while (0)

__device__ __forceinline__ uint32_t smem_u32(const void* p) { return (uint32_t)__cvta_generic_to_shared(p); }
__device__ __forceinline__ bool elect_one() {
  uint32_t p;
  asm volatile("{\n.reg .pred p;\nelect.sync _|p, 0xffffffff;\nselp.u32 %0, 1, 0, p;\n}\n" : "=r"(p));
  return p != 0;
}
__device__ __forceinline__ void mbar_init(uint32_t bar, uint32_t cnt) {
  asm volatile("mbarrier.init.shared::cta.b64 [%0], %1;" :: "r"(bar), "r"(cnt));
}
__device__ __forceinline__ void mbar_expect_tx(uint32_t bar, uint32_t bytes) {
  asm volatile("mbarrier.arrive.expect_tx.shared::cta.b64 _, [%0], %1;" :: "r"(bar), "r"(bytes) : "memory");
}
#define mbar_wait(bar, parity) \
  asm volatile("{\n.reg .pred p, q;\nW_%=:\nmbarrier.try_wait.parity.shared::cta.b64 p, [%1], %2;\nadd.s32 %0, %0, -1;\n" \
               "setp.gt.and.s32 q, %0, 0, !p;\n@q bra.uni W_%=;\n}\n" : "+r"(budget) : "r"((uint32_t)(bar)), "r"((uint32_t)(parity)) : "memory")
#define mbar_wait_sl(bar, parity) \
  asm volatile("{\n.reg .pred p, q;\nW_%=:\nmbarrier.try_wait.parity.shared::cta.b64 p, [%1], %2, 20000;\nadd.s32 %0, %0, -64;\n" \
               "setp.gt.and.s32 q, %0, 0, !p;\n@q bra.uni W_%=;\n}\n" : "+r"(budget) : "r"((uint32_t)(bar)), "r"((uint32_t)(parity)) : "memory")
__device__ __forceinline__ void mbar_arrive_local(uint32_t bar) {
  asm volatile("mbarrier.arrive.shared::cta.b64 _, [%0];" :: "r"(bar) : "memory");
}
__device__ __forceinline__ void tma_load_2d(uint32_t dst, const CUtensorMap* tm, uint32_t bar, int c0, int c1) {
  asm volatile("cp.async.bulk.tensor.2d.shared::cluster.global.mbarrier::complete_tx::bytes [%0], [%1, {%3, %4}], [%2];"
               :: "r"(dst), "l"(tm), "r"(bar), "r"(c0), "r"(c1) : "memory");
}
__device__ __forceinline__ void tma_load_2d_mc(uint32_t dst, const CUtensorMap* tm, uint32_t bar, int c0, int c1) {
  asm volatile("cp.async.bulk.tensor.2d.shared::cluster.global.mbarrier::complete_tx::bytes.multicast::cluster [%0], [%1, {%3, %4}], [%2], %5;"
               :: "r"(dst), "l"(tm), "r"(bar), "r"(c0), "r"(c1), "h"((uint16_t)3) : "memory");
}
__device__ __forceinline__ void tma_store_2d(const CUtensorMap* tm, uint32_t src, int c0, int c1) {
  asm volatile("cp.async.bulk.tensor.2d.global.shared::cta.bulk_group [%0, {%2, %3}], [%1];"
               :: "l"(tm), "r"(src), "r"(c0), "r"(c1) : "memory");
}
__device__ __forceinline__ void bulk_commit_wait() {
  asm volatile("cp.async.bulk.commit_group;\ncp.async.bulk.wait_group 0;" ::: "memory");
}
__device__ __forceinline__ void prefetch_tmap(const CUtensorMap* tm) {
  asm volatile("prefetch.tensormap [%0];" :: "l"(tm) : "memory");
}
__device__ __forceinline__ void fence_proxy_async_global() { asm volatile("fence.proxy.async.global;" ::: "memory"); }
__device__ __forceinline__ void fence_proxy_async_smem() { asm volatile("fence.proxy.async.shared::cta;" ::: "memory"); }
__device__ __forceinline__ unsigned ld_relaxed(const unsigned* p) {
  unsigned v;
  asm volatile("ld.relaxed.gpu.global.u32 %0, [%1];" : "=r"(v) : "l"(p) : "memory");
  return v;
}
__device__ __forceinline__ void fence_acquire() { asm volatile("fence.acquire.gpu;" ::: "memory"); }
__device__ __forceinline__ void wait_flag(const unsigned* p, unsigned target) {
  int it = 0;
  while ((int)(ld_relaxed(p) - target) < 0 && ++it < (1 << 20)) {}
  fence_acquire();
}
__device__ __forceinline__ void signal_release(unsigned* p) {
  asm volatile("red.release.gpu.global.add.u32 [%0], 1;" :: "l"(p) : "memory");
}
template <int ID, int N> __device__ __forceinline__ void bar_arrive() { asm volatile("bar.arrive %0, %1;" :: "n"(ID), "n"(N) : "memory"); }
template <int ID, int N> __device__ __forceinline__ void bar_sync() { asm volatile("bar.sync %0, %1;" :: "n"(ID), "n"(N) : "memory"); }
__device__ __forceinline__ void bar_wg(int wg) { asm volatile("bar.sync %0, 128;" :: "r"(2 + wg) : "memory"); }
__device__ __forceinline__ void cluster_sync() {
  asm volatile("barrier.cluster.arrive.relaxed.aligned;\nbarrier.cluster.wait.aligned;" ::: "memory");
}
__device__ __forceinline__ void cluster_wait() { asm volatile("barrier.cluster.wait.acquire.aligned;" ::: "memory"); }
enum { BAR_KV = 4  , BAR_O = 7  , BAR_WF = 12  , BAR_SKEW = 13 };

__device__ __forceinline__ void wgmma_fence() { asm volatile("wgmma.fence.sync.aligned;" ::: "memory"); }
__device__ __forceinline__ void wgmma_commit() { asm volatile("wgmma.commit_group.sync.aligned;" ::: "memory"); }
template <int N> __device__ __forceinline__ void wgmma_wait() { asm volatile("wgmma.wait_group.sync.aligned %0;" :: "n"(N) : "memory"); }

template <int scale_d, int tnsp_b = 1> __device__ __forceinline__ void wgmma_n192(float* d, uint64_t descA, uint64_t descB) {
  asm volatile("{\n.reg .pred p;\nsetp.ne.b32 p, %98, 0;\n"
               "wgmma.mma_async.sync.aligned.m64n192k16.f32.bf16.bf16 {%0,%1,%2,%3,%4,%5,%6,%7,%8,%9,%10,%11,%12,%13,%14,%15,%16,%17,%18,%19,%20,%21,%22,%23,%24,%25,%26,%27,%28,%29,%30,%31,%32,%33,%34,%35,%36,%37,%38,%39,%40,%41,%42,%43,%44,%45,%46,%47,%48,%49,%50,%51,%52,%53,%54,%55,%56,%57,%58,%59,%60,%61,%62,%63,%64,%65,%66,%67,%68,%69,%70,%71,%72,%73,%74,%75,%76,%77,%78,%79,%80,%81,%82,%83,%84,%85,%86,%87,%88,%89,%90,%91,%92,%93,%94,%95}, %96, %97, p, 1, 1, 0, %99;\n}\n"
               : "+f"(d[0]), "+f"(d[1]), "+f"(d[2]), "+f"(d[3]), "+f"(d[4]), "+f"(d[5]), "+f"(d[6]), "+f"(d[7]), "+f"(d[8]), "+f"(d[9]), "+f"(d[10]), "+f"(d[11]), "+f"(d[12]), "+f"(d[13]), "+f"(d[14]), "+f"(d[15]), "+f"(d[16]), "+f"(d[17]), "+f"(d[18]), "+f"(d[19]), "+f"(d[20]), "+f"(d[21]), "+f"(d[22]), "+f"(d[23]), "+f"(d[24]), "+f"(d[25]), "+f"(d[26]), "+f"(d[27]), "+f"(d[28]), "+f"(d[29]), "+f"(d[30]), "+f"(d[31]), "+f"(d[32]), "+f"(d[33]), "+f"(d[34]), "+f"(d[35]), "+f"(d[36]), "+f"(d[37]), "+f"(d[38]), "+f"(d[39]), "+f"(d[40]), "+f"(d[41]), "+f"(d[42]), "+f"(d[43]), "+f"(d[44]), "+f"(d[45]), "+f"(d[46]), "+f"(d[47]), "+f"(d[48]), "+f"(d[49]), "+f"(d[50]), "+f"(d[51]), "+f"(d[52]), "+f"(d[53]), "+f"(d[54]), "+f"(d[55]), "+f"(d[56]), "+f"(d[57]), "+f"(d[58]), "+f"(d[59]), "+f"(d[60]), "+f"(d[61]), "+f"(d[62]), "+f"(d[63]), "+f"(d[64]), "+f"(d[65]), "+f"(d[66]), "+f"(d[67]), "+f"(d[68]), "+f"(d[69]), "+f"(d[70]), "+f"(d[71]), "+f"(d[72]), "+f"(d[73]), "+f"(d[74]), "+f"(d[75]), "+f"(d[76]), "+f"(d[77]), "+f"(d[78]), "+f"(d[79]), "+f"(d[80]), "+f"(d[81]), "+f"(d[82]), "+f"(d[83]), "+f"(d[84]), "+f"(d[85]), "+f"(d[86]), "+f"(d[87]), "+f"(d[88]), "+f"(d[89]), "+f"(d[90]), "+f"(d[91]), "+f"(d[92]), "+f"(d[93]), "+f"(d[94]), "+f"(d[95])
               : "l"(descA), "l"(descB), "n"(scale_d), "n"(tnsp_b));
}
template <int scale_d> __device__ __forceinline__ void wgmma4_n192(float* d, uint32_t da, uint32_t db) {
#define R_ "{%0,%1,%2,%3,%4,%5,%6,%7,%8,%9,%10,%11,%12,%13,%14,%15,%16,%17,%18,%19,%20,%21,%22,%23,%24,%25,%26,%27,%28,%29,%30,%31,%32,%33,%34,%35,%36,%37,%38,%39,%40,%41,%42,%43,%44,%45,%46,%47,%48,%49,%50,%51,%52,%53,%54,%55,%56,%57,%58,%59,%60,%61,%62,%63,%64,%65,%66,%67,%68,%69,%70,%71,%72,%73,%74,%75,%76,%77,%78,%79,%80,%81,%82,%83,%84,%85,%86,%87,%88,%89,%90,%91,%92,%93,%94,%95}"
  asm volatile("{\n.reg .pred p, q;\n.reg .b64 a, b;\nsetp.ne.b32 p, %98, 0;\nsetp.eq.b32 q, 0, 0;\nmov.b64 a, {%96, 0x40000040};\nmov.b64 b, {%97, 0x40000040};\n"
               "wgmma.mma_async.sync.aligned.m64n192k16.f32.bf16.bf16 " R_ ", a, b, p, 1, 1, 0, 1;\nadd.s64 a, a, 2;\nadd.s64 b, b, 128;\n"
               "wgmma.mma_async.sync.aligned.m64n192k16.f32.bf16.bf16 " R_ ", a, b, q, 1, 1, 0, 1;\nadd.s64 a, a, 2;\nadd.s64 b, b, 128;\n"
               "wgmma.mma_async.sync.aligned.m64n192k16.f32.bf16.bf16 " R_ ", a, b, q, 1, 1, 0, 1;\nadd.s64 a, a, 2;\nadd.s64 b, b, 128;\n"
               "wgmma.mma_async.sync.aligned.m64n192k16.f32.bf16.bf16 " R_ ", a, b, q, 1, 1, 0, 1;\n}\n"
               : "+f"(d[0]), "+f"(d[1]), "+f"(d[2]), "+f"(d[3]), "+f"(d[4]), "+f"(d[5]), "+f"(d[6]), "+f"(d[7]), "+f"(d[8]), "+f"(d[9]), "+f"(d[10]), "+f"(d[11]), "+f"(d[12]), "+f"(d[13]), "+f"(d[14]), "+f"(d[15]), "+f"(d[16]), "+f"(d[17]), "+f"(d[18]), "+f"(d[19]), "+f"(d[20]), "+f"(d[21]), "+f"(d[22]), "+f"(d[23]), "+f"(d[24]), "+f"(d[25]), "+f"(d[26]), "+f"(d[27]), "+f"(d[28]), "+f"(d[29]), "+f"(d[30]), "+f"(d[31]), "+f"(d[32]), "+f"(d[33]), "+f"(d[34]), "+f"(d[35]), "+f"(d[36]), "+f"(d[37]), "+f"(d[38]), "+f"(d[39]), "+f"(d[40]), "+f"(d[41]), "+f"(d[42]), "+f"(d[43]), "+f"(d[44]), "+f"(d[45]), "+f"(d[46]), "+f"(d[47]), "+f"(d[48]), "+f"(d[49]), "+f"(d[50]), "+f"(d[51]), "+f"(d[52]), "+f"(d[53]), "+f"(d[54]), "+f"(d[55]), "+f"(d[56]), "+f"(d[57]), "+f"(d[58]), "+f"(d[59]), "+f"(d[60]), "+f"(d[61]), "+f"(d[62]), "+f"(d[63]), "+f"(d[64]), "+f"(d[65]), "+f"(d[66]), "+f"(d[67]), "+f"(d[68]), "+f"(d[69]), "+f"(d[70]), "+f"(d[71]), "+f"(d[72]), "+f"(d[73]), "+f"(d[74]), "+f"(d[75]), "+f"(d[76]), "+f"(d[77]), "+f"(d[78]), "+f"(d[79]), "+f"(d[80]), "+f"(d[81]), "+f"(d[82]), "+f"(d[83]), "+f"(d[84]), "+f"(d[85]), "+f"(d[86]), "+f"(d[87]), "+f"(d[88]), "+f"(d[89]), "+f"(d[90]), "+f"(d[91]), "+f"(d[92]), "+f"(d[93]), "+f"(d[94]), "+f"(d[95])
               : "r"(da), "r"(db), "n"(scale_d));
#undef R_
}
template <int scale_d> __device__ __forceinline__ void wgmma4_n128(float* d, uint32_t da, uint32_t db) {
#define R_ "{%0,%1,%2,%3,%4,%5,%6,%7,%8,%9,%10,%11,%12,%13,%14,%15,%16,%17,%18,%19,%20,%21,%22,%23,%24,%25,%26,%27,%28,%29,%30,%31,%32,%33,%34,%35,%36,%37,%38,%39,%40,%41,%42,%43,%44,%45,%46,%47,%48,%49,%50,%51,%52,%53,%54,%55,%56,%57,%58,%59,%60,%61,%62,%63}"
  asm volatile("{\n.reg .pred p, q;\n.reg .b64 a, b;\nsetp.ne.b32 p, %66, 0;\nsetp.eq.b32 q, 0, 0;\nmov.b64 a, {%64, 0x40000040};\nmov.b64 b, {%65, 0x40000040};\n"
               "wgmma.mma_async.sync.aligned.m64n128k16.f32.bf16.bf16 " R_ ", a, b, p, 1, 1, 0, 1;\nadd.s64 a, a, 2;\nadd.s64 b, b, 128;\n"
               "wgmma.mma_async.sync.aligned.m64n128k16.f32.bf16.bf16 " R_ ", a, b, q, 1, 1, 0, 1;\nadd.s64 a, a, 2;\nadd.s64 b, b, 128;\n"
               "wgmma.mma_async.sync.aligned.m64n128k16.f32.bf16.bf16 " R_ ", a, b, q, 1, 1, 0, 1;\nadd.s64 a, a, 2;\nadd.s64 b, b, 128;\n"
               "wgmma.mma_async.sync.aligned.m64n128k16.f32.bf16.bf16 " R_ ", a, b, q, 1, 1, 0, 1;\n}\n"
               : "+f"(d[0]), "+f"(d[1]), "+f"(d[2]), "+f"(d[3]), "+f"(d[4]), "+f"(d[5]), "+f"(d[6]), "+f"(d[7]), "+f"(d[8]), "+f"(d[9]), "+f"(d[10]), "+f"(d[11]), "+f"(d[12]), "+f"(d[13]), "+f"(d[14]), "+f"(d[15]), "+f"(d[16]), "+f"(d[17]), "+f"(d[18]), "+f"(d[19]), "+f"(d[20]), "+f"(d[21]), "+f"(d[22]), "+f"(d[23]), "+f"(d[24]), "+f"(d[25]), "+f"(d[26]), "+f"(d[27]), "+f"(d[28]), "+f"(d[29]), "+f"(d[30]), "+f"(d[31]), "+f"(d[32]), "+f"(d[33]), "+f"(d[34]), "+f"(d[35]), "+f"(d[36]), "+f"(d[37]), "+f"(d[38]), "+f"(d[39]), "+f"(d[40]), "+f"(d[41]), "+f"(d[42]), "+f"(d[43]), "+f"(d[44]), "+f"(d[45]), "+f"(d[46]), "+f"(d[47]), "+f"(d[48]), "+f"(d[49]), "+f"(d[50]), "+f"(d[51]), "+f"(d[52]), "+f"(d[53]), "+f"(d[54]), "+f"(d[55]), "+f"(d[56]), "+f"(d[57]), "+f"(d[58]), "+f"(d[59]), "+f"(d[60]), "+f"(d[61]), "+f"(d[62]), "+f"(d[63])
               : "r"(da), "r"(db), "n"(scale_d));
#undef R_
}
template <int scale_d> __device__ __forceinline__ void wgmma_n32(float* d, uint64_t descA, uint64_t descB) {
  asm volatile("{\n.reg .pred p;\nsetp.ne.b32 p, %18, 0;\n"
               "wgmma.mma_async.sync.aligned.m64n32k16.f32.bf16.bf16 {%0,%1,%2,%3,%4,%5,%6,%7,%8,%9,%10,%11,%12,%13,%14,%15}, %16, %17, p, 1, 1, 0, 1;\n}\n"
               : "+f"(d[0]), "+f"(d[1]), "+f"(d[2]), "+f"(d[3]), "+f"(d[4]), "+f"(d[5]), "+f"(d[6]), "+f"(d[7]), "+f"(d[8]), "+f"(d[9]), "+f"(d[10]), "+f"(d[11]), "+f"(d[12]), "+f"(d[13]), "+f"(d[14]), "+f"(d[15])
               : "l"(descA), "l"(descB), "n"(scale_d));
}
template <int scale_d, int tnsp_a> __device__ __forceinline__ void wgmma_n40(float* d, uint64_t descA, uint64_t descB) {
  asm volatile("{\n.reg .pred p;\nsetp.ne.b32 p, %22, 0;\n"
               "wgmma.mma_async.sync.aligned.m64n40k16.f32.bf16.bf16 {%0,%1,%2,%3,%4,%5,%6,%7,%8,%9,%10,%11,%12,%13,%14,%15,%16,%17,%18,%19}, %20, %21, p, 1, 1, %23, 1;\n}\n"
               : "+f"(d[0]), "+f"(d[1]), "+f"(d[2]), "+f"(d[3]), "+f"(d[4]), "+f"(d[5]), "+f"(d[6]), "+f"(d[7]), "+f"(d[8]), "+f"(d[9]), "+f"(d[10]), "+f"(d[11]), "+f"(d[12]), "+f"(d[13]), "+f"(d[14]), "+f"(d[15]), "+f"(d[16]), "+f"(d[17]), "+f"(d[18]), "+f"(d[19])
               : "l"(descA), "l"(descB), "n"(scale_d), "n"(tnsp_a));
}
template <int scale_d> __device__ __forceinline__ void wgmma_n40_rs(float* d, const uint32_t* a, uint64_t descB) {
  asm volatile("{\n.reg .pred p;\nsetp.ne.b32 p, %25, 0;\n"
               "wgmma.mma_async.sync.aligned.m64n40k16.f32.bf16.bf16 {%0,%1,%2,%3,%4,%5,%6,%7,%8,%9,%10,%11,%12,%13,%14,%15,%16,%17,%18,%19}, {%20,%21,%22,%23}, %24, p, 1, 1, 1;\n}\n"
               : "+f"(d[0]), "+f"(d[1]), "+f"(d[2]), "+f"(d[3]), "+f"(d[4]), "+f"(d[5]), "+f"(d[6]), "+f"(d[7]), "+f"(d[8]), "+f"(d[9]), "+f"(d[10]), "+f"(d[11]), "+f"(d[12]), "+f"(d[13]), "+f"(d[14]), "+f"(d[15]), "+f"(d[16]), "+f"(d[17]), "+f"(d[18]), "+f"(d[19])
               : "r"(a[0]), "r"(a[1]), "r"(a[2]), "r"(a[3]), "l"(descB), "n"(scale_d));
}
__device__ __forceinline__ uint64_t make_desc(uint32_t addr, uint32_t lbo_bytes, uint32_t sbo_bytes) {
  return (uint64_t)((addr & 0x3FFFF) >> 4) | ((uint64_t)(lbo_bytes >> 4) << 16) | ((uint64_t)(sbo_bytes >> 4) << 32) | (1ull << 62);
}

__device__ __forceinline__ void ldsm_x4(uint32_t addr, uint32_t& r0, uint32_t& r1, uint32_t& r2, uint32_t& r3) {
  asm volatile("ldmatrix.sync.aligned.m8n8.x4.shared.b16 {%0,%1,%2,%3}, [%4];" : "=r"(r0), "=r"(r1), "=r"(r2), "=r"(r3) : "r"(addr) : "memory");
}
__device__ __forceinline__ void ldsm_x4_t(uint32_t addr, uint32_t& r0, uint32_t& r1, uint32_t& r2, uint32_t& r3) {
  asm volatile("ldmatrix.sync.aligned.m8n8.x4.trans.shared.b16 {%0,%1,%2,%3}, [%4];" : "=r"(r0), "=r"(r1), "=r"(r2), "=r"(r3) : "r"(addr) : "memory");
}
__device__ __forceinline__ void stsm_x4(uint32_t addr, uint32_t r0, uint32_t r1, uint32_t r2, uint32_t r3) {
  asm volatile("stmatrix.sync.aligned.m8n8.x4.shared.b16 [%0], {%1,%2,%3,%4};" :: "r"(addr), "r"(r0), "r"(r1), "r"(r2), "r"(r3) : "memory");
}
__device__ __forceinline__ void sts128(uint32_t addr, uint32_t a, uint32_t b, uint32_t c, uint32_t d) {
  asm volatile("st.shared.v4.u32 [%0], {%1,%2,%3,%4};" :: "r"(addr), "r"(a), "r"(b), "r"(c), "r"(d) : "memory");
}
__device__ __forceinline__ float lds32f(uint32_t addr) {
  float v;
  asm volatile("ld.shared.f32 %0, [%1];" : "=f"(v) : "r"(addr) : "memory");
  return v;
}
__device__ __forceinline__ void sts32f(uint32_t addr, float a) {
  asm volatile("st.shared.f32 [%0], %1;" :: "r"(addr), "f"(a) : "memory");
}
__device__ __forceinline__ void mma_bf16(float (&c)[4], uint32_t a0, uint32_t a1, uint32_t a2, uint32_t a3, uint32_t b0, uint32_t b1) {
  asm volatile("mma.sync.aligned.m16n8k16.row.col.f32.bf16.bf16.f32 {%0,%1,%2,%3}, {%4,%5,%6,%7}, {%8,%9}, {%0,%1,%2,%3};"
               : "+f"(c[0]), "+f"(c[1]), "+f"(c[2]), "+f"(c[3]) : "r"(a0), "r"(a1), "r"(a2), "r"(a3), "r"(b0), "r"(b1));
}
__device__ __forceinline__ uint32_t pack_bf16(float lo, float hi) {
  uint32_t r;
  asm("cvt.rn.bf16x2.f32 %0, %1, %2;" : "=r"(r) : "f"(hi), "f"(lo));
  return r;
}
__device__ __forceinline__ float bf_lo(uint32_t v) { return __uint_as_float(v << 16); }
__device__ __forceinline__ float bf_hi(uint32_t v) { return __uint_as_float(v & 0xFFFF0000u); }
__device__ __forceinline__ void split3(float x, uint32_t& h, uint32_t& m, uint32_t& l) {
  h = pack_bf16(x, 0.f); x -= bf_lo(h);
  m = pack_bf16(x, 0.f); x -= bf_lo(m);
  l = pack_bf16(x, 0.f);
}
__device__ __forceinline__ float ex2(float x) { float r; asm("ex2.approx.ftz.f32 %0, %1;" : "=f"(r) : "f"(x)); return r; }
__device__ __forceinline__ float rcp_fast(float x) { float r; asm("rcp.approx.ftz.f32 %0, %1;" : "=f"(r) : "f"(x)); return r; }
__device__ __forceinline__ void red_v4(float* p, float a, float b, float c, float d) {
  asm volatile("red.global.add.v4.f32 [%0], {%1, %2, %3, %4};" :: "l"(p), "f"(a), "f"(b), "f"(c), "f"(d) : "memory");
}
__device__ __forceinline__ uint4 ld_ll(const uint4* p) {
  uint4 v;
  asm volatile("{\n.reg .b64 a, b;\nld.relaxed.gpu.global.v2.b64 {a, b}, [%4];\nmov.b64 {%0, %1}, a;\nmov.b64 {%2, %3}, b;\n}\n"
               : "=r"(v.x), "=r"(v.y), "=r"(v.z), "=r"(v.w) : "l"(p) : "memory");
  return v;
}
__device__ __forceinline__ void st_b64(uint2* p, uint32_t a, uint32_t b) {
  asm volatile("{\n.reg .b64 v;\nmov.b64 v, {%1, %2};\nst.relaxed.gpu.global.b64 [%0], v;\n}\n" :: "l"(p), "r"(a), "r"(b) : "memory");
}
__device__ __forceinline__ void st_b128(uint4* p, uint32_t a, uint32_t b, uint32_t c, uint32_t d) {
  asm volatile("{\n.reg .b128 v;\nmov.b128 v, {%1, %2, %3, %4};\nst.relaxed.gpu.global.b128 [%0], v;\n}\n" :: "l"(p), "r"(a), "r"(b), "r"(c), "r"(d) : "memory");
}
__device__ __forceinline__ uint4 ld_b128(const uint4* p) {
  uint4 v;
  asm volatile("{\n.reg .b128 v;\nld.relaxed.gpu.global.b128 v, [%4];\nmov.b128 {%0, %1, %2, %3}, v;\n}\n" : "=r"(v.x), "=r"(v.y), "=r"(v.z), "=r"(v.w) : "l"(p) : "memory");
  return v;
}

constexpr float LOG2E = 1.4426950408889634f;

struct Params {
  const __nv_bfloat16* x0;
  const __nv_bfloat16* wA_qkv;
  const __nv_bfloat16* wA_o;
  const __nv_bfloat16* wB_qkv;
  const __nv_bfloat16* wB_phi;
  const __nv_bfloat16* wB_o;
  __nv_bfloat16* out;
};

#define ACC_DEF(d, n) _Pragma("unroll") for (int i_ = 0; i_ < (n); i_++) asm volatile("" : "=f"(d[i_]))
#define ACC_FENCE(d, n) _Pragma("unroll") for (int i_ = 0; i_ < (n); i_++) asm volatile("" : "+f"(d[i_]) :: "memory")
#define PIN(a, n) _Pragma("unroll") for (int i_ = 0; i_ < (n); i_++) asm volatile("" : "+f"((a)[i_]))
#define PINU(a, n) _Pragma("unroll") for (int i_ = 0; i_ < (n); i_++) asm volatile("" : "+r"((a)[i_]))

#define STAGE64(acc, off, p0, KIND, SEND) { \
    uint32_t w_[4][4]; \
    _Pragma("unroll") for (int j_ = 0; j_ < 4; j_++) { \
      const int o_ = (off) + j_ * 8; \
      w_[j_][0] = pack_bf16(rs0 * acc[o_ + 0], rs0 * acc[o_ + 1]); \
      w_[j_][1] = pack_bf16(rs1 * acc[o_ + 2], rs1 * acc[o_ + 3]); \
      w_[j_][2] = pack_bf16(rs0 * acc[o_ + 4], rs0 * acc[o_ + 5]); \
      w_[j_][3] = pack_bf16(rs1 * acc[o_ + 6], rs1 * acc[o_ + 7]); \
    } \
    if ((SEND) && hsend) { \
      _Pragma("unroll") for (int j_ = 0; j_ < 4; j_++) { \
        w_[j_][0] = (w_[j_][0] & ~1u) | hbit; \
        st_b128(hbase + lane + ((KIND) * 4 + j_) * 32, w_[j_][0], w_[j_][1], w_[j_][2], w_[j_][3]); \
      } \
    } \
    _Pragma("unroll") for (int j_ = 0; j_ < 4; j_++) \
      stsm_x4((KIND) ? (p0) + (j_ >> 1) * 8192 + (srowoff >> 1) + ((((uint32_t)(j_ & 1) << 5) + lhi) ^ lsw2) \
                     : (p0) + srowoff + ((((uint32_t)j_ << 5) + lhi) ^ lsw), \
              w_[j_][0], w_[j_][1], w_[j_][2], w_[j_][3]); \
  }
#define RW(j) (((j) >> 1) * 4 + ((j) & 1))
__device__ __forceinline__ float rmax16(const float* p) {
  float m[4];
#pragma unroll
  for (int j = 0; j < 4; j++) m[j] = fmaxf(fmaxf(p[RW(j)], p[RW(j + 4)]), fmaxf(p[RW(j + 8)], p[RW(j + 12)]));
  const float r = fmaxf(fmaxf(m[0], m[1]), fmaxf(m[2], m[3]));
  return fmaxf(r, __shfl_xor_sync(0xffffffffu, r, 1));
}
__device__ __forceinline__ float rmin16(const float* p) {
  float m[4];
#pragma unroll
  for (int j = 0; j < 4; j++) m[j] = fminf(fminf(p[RW(j)], p[RW(j + 4)]), fminf(p[RW(j + 8)], p[RW(j + 12)]));
  const float r = fminf(fminf(m[0], m[1]), fminf(m[2], m[3]));
  return fminf(r, __shfl_xor_sync(0xffffffffu, r, 1));
}
__device__ __forceinline__ float exps16(float* o, const float* p, float c, float b) {
  float s[4];
#pragma unroll
  for (int j = 0; j < 16; j++) { o[j] = ex2(fmaf(p[RW(j)], c, b)); if (j < 4) s[j] = o[j]; else s[j & 3] += o[j]; }
  return (s[0] + s[1]) + (s[2] + s[3]);
}
__device__ __forceinline__ void store16(const float* e, float sum, uint32_t dst, uint32_t dsw, int c0) {
  const float inv = rcp_fast(sum + __shfl_xor_sync(0xffffffffu, sum, 1));
#pragma unroll
  for (int j = 0; j < 2; j++)
    sts128(dst + (((c0 + j) << 4) ^ dsw), pack_bf16(e[j * 8] * inv, e[j * 8 + 1] * inv), pack_bf16(e[j * 8 + 2] * inv, e[j * 8 + 3] * inv),
           pack_bf16(e[j * 8 + 4] * inv, e[j * 8 + 5] * inv), pack_bf16(e[j * 8 + 6] * inv, e[j * 8 + 7] * inv));
}
__device__ __forceinline__ void expp16(uint32_t* o, const float* p, float c0, float b0, float c1, float b1) {
#pragma unroll
  for (int j = 0; j < 8; j++) {
    const float c = (j & 1) ? c1 : c0, b = (j & 1) ? b1 : b0;
    o[j] = pack_bf16(ex2(fmaf(p[2 * j], c, b)), ex2(fmaf(p[2 * j + 1], c, b)));
  }
}
__device__ __forceinline__ void extrema(float* m, const float* p, float c0, float c1) {
#pragma unroll
  for (int i = 0; i < 4; i++) {
    const float* q = p + (i >> 1) * 16 + (i & 1) * 2;
    m[(i >> 1) * 4 + (i & 1)] = fminf(fminf(fminf(q[0], q[1]), fminf(q[4], q[5])), fminf(fminf(q[8], q[9]), fminf(q[12], q[13])));
    m[(i >> 1) * 4 + (i & 1) + 2] = fmaxf(fmaxf(fmaxf(q[0], q[1]), fmaxf(q[4], q[5])), fmaxf(fmaxf(q[8], q[9]), fmaxf(q[12], q[13])));
  }
#pragma unroll
  for (int o = 1; o <= 2; o <<= 1)
#pragma unroll
    for (int i = 0; i < 8; i++) { const float x = __shfl_xor_sync(0xffffffffu, m[i], o); m[i] = (i & 2) ? fmaxf(m[i], x) : fminf(m[i], x); }
#pragma unroll
  for (int i = 0; i < 8; i++) m[i] *= ((i & 2) ? -1.f : 1.f) * ((i & 1) ? c1 : c0);
}
#define SCHED_FENCE() asm volatile("pmevent 0;" ::: "memory")

__global__ void __cluster_dims__(2, 1, 1) __launch_bounds__(384, 1)
mega_kernel(const __grid_constant__ CUtensorMap tm_x0, const __grid_constant__ CUtensorMap tm_xo, const __grid_constant__ CUtensorMap tm_os,
            const __grid_constant__ CUtensorMap tm_o, const __grid_constant__ CUtensorMap tm_wf,
            const __grid_constant__ CUtensorMap tm_wqA, const __grid_constant__ CUtensorMap tm_wqB,
            const __grid_constant__ CUtensorMap tm_woA, const __grid_constant__ CUtensorMap tm_woB,
            const __grid_constant__ CUtensorMap tm_phi, const Params prm) {
  extern __shared__ __align__(1024) uint8_t smem_raw[];
  const uint32_t sbase = smem_u32(smem_raw);
  const uint32_t bar_full = sbase + OFF_BAR;
  const uint32_t bar_done = bar_full + 384;
  const uint32_t bar_stat = bar_full + 768, bar_stat2 = bar_full + 776, bar_epi = bar_full + 784, bar_phi = bar_full + 936  ;
  const uint32_t bar_xr = bar_full + 800, bar_lx = bar_full + 808, bar_kvf = bar_full + 816  , bar_stg = bar_full + 832;
  const uint32_t bar_chk = bar_full + 848;

  const int warp = __shfl_sync(0xffffffffu, threadIdx.x >> 5, 0), lane = threadIdx.x & 31;
  uint32_t rank;
  asm volatile("mov.u32 %0, %%cluster_ctarank;" : "=r"(rank));
  const int aux = (int)blockIdx.x - NMAIN, tp = (int)(blockIdx.x >> 1) - 4;
  const int gp = tp < 0 ? 0 : (tp < 32 ? tp & 7 : 1 + (tp - 32) % 7), me = tp < 0 ? tp + 8 : (tp < 32 ? tp >> 3 : 4 + (tp - 32) / 7);
  const int jj = me, cc = gp;
  const int cta = aux >= 0 ? -1 : (cc * 8 + jj) * 2 + (int)rank;
  const int mm = cc * 2 + (int)rank;

#define LOAD_EPOCH() const unsigned epoch = ld_relaxed(&g_flags.epoch.v), ep1 = epoch + 1; (void)epoch
  int budget = 1 << 22;

  if (cta >= 0) {
    {
      const int tx = threadIdx.x;
      const __nv_bfloat16* pf = (tx < 128) ? prm.x0 + (size_t)(mm * 128 + tx) * D_MODEL + jj * 128
                                           : prm.wA_qkv + (size_t)(jj * 128 + (tx & 63)) * 3072 + ((tx - 128) >> 6) * 1024 + jj * 128 + rank * 64;
      if (tx < 320) asm volatile("prefetch.global.L2 [%0];" :: "l"(pf));
      else if (tx == 320) prefetch_tmap(&tm_x0);
      else if (tx == 352) prefetch_tmap(&tm_wqA);
      else if (tx == 383) asm volatile("prefetch.global.L2 [%0];" :: "l"(&g_flags.epoch.v));
    }
    if (elect_one()) {
#pragma unroll
      for (int i = 0; i < 4; i++) {
        const int u = warp * 4 + i;
        mbar_init(bar_full + u * 8, ((u >= 4 && u < 11) || (u > 32 && u != 40)) ? 2 : 1); mbar_init(bar_done + u * 8, 16);
      }
      mbar_init(bar_stat + warp * 16, 0x111111181182ull >> (4 * warp) & 15);
      mbar_init(bar_stat + warp * 16 + 8, 0x111111121811ull >> (4 * warp) & 15);
      mbar_init(bar_chk + 112 + (warp & 7) * 8, 1);
      asm volatile("fence.mbarrier_init.release.cluster;" ::: "memory");
    }
    __syncthreads();
    asm volatile("barrier.cluster.arrive.relaxed.aligned;" ::: "memory");
  }

  if (cta < 0) {
    LOAD_EPOCH();
    const uint32_t buf = sbase + warp * SLOT, bar = sbase + OFF_BAR + warp * 16;
    const uint32_t lsw = (lane & 7) << 4, lhi = (lane >> 4) << 4, lrow = (lane & 15) * 128;
    const bool el = elect_one();
    if (el) {
      mbar_init(bar, 1); mbar_init(bar + 8, 1);
      asm volatile("fence.mbarrier_init.release.cluster;" ::: "memory");
    }
#pragma unroll 1
    for (int rd = 0; rd < (NLAYERS > 1 ? 5 : 2); rd++) {
      if (rd >= 2 && warp >= 8) break;
      const int tk = rd < 2 ? aux * 12 + warp : aux * 8 + warp;
      const int half = tk & 1;
      const int blk = rd < 2 ? (tk >> 1) * 2 + rd : (4 - rd) * 16 + (tk >> 1);
      const CUtensorMap* tm = rd < 2 ? &tm_wqA : (rd == 2 ? &tm_wqB : &tm_wf);
      const int j0 = (blk & 15) >> 1;
#define AUX_LOAD(n) { const uint32_t d_ = buf + ((n) & 1) * 8192, b_ = bar + ((n) & 1) * 8; const int r_ = kslice(j0, 2 * (n) + half) * 64; \
        mbar_expect_tx(b_, 8192); tma_load_2d(d_, tm, b_, blk * 64, r_); tma_load_2d(d_ + 4096, tm, b_, blk * 64, r_ + 32); }
      if (el) {
        if (rd == 3) { wait_flag(&g_flags.wfready[j0].v, ep1 * 16); fence_proxy_async_global(); }
        AUX_LOAD(0); AUX_LOAD(1);
      }
      __syncwarp();
      float cs[8][4];
#pragma unroll
      for (int i = 0; i < 8; i++) cs[i][0] = cs[i][1] = cs[i][2] = cs[i][3] = 0.f;
#pragma unroll 1
      for (int n = 0; n < 8; n++) {
        const uint32_t tb = buf + (n & 1) * 8192 + lrow;
        mbar_wait(bar + (n & 1) * 8, (n >> 1) & 1);
#pragma unroll
        for (int i = 0; i < 16; i++) {
          uint32_t b0, b1, b2, b3;
          ldsm_x4_t(tb + (i >> 2) * 2048 + (((i & 3) * 32 + lhi) ^ lsw), b0, b1, b2, b3);
          mma_bf16(cs[2 * (i & 3)], 0x3F803F80u, 0x3F803F80u, 0x3F803F80u, 0x3F803F80u, b0, b1);
          mma_bf16(cs[2 * (i & 3) + 1], 0x3F803F80u, 0x3F803F80u, 0x3F803F80u, 0x3F803F80u, b2, b3);
        }
        __syncwarp();
        if (el && n < 6) AUX_LOAD(n + 2);
        __syncwarp();
      }
      if (lane < 4) {
#pragma unroll
        for (int i = 0; i < 8; i++) st_b64(&g_colsum[rd >= 2][blk * 32 + i * 4 + lane][half], __float_as_uint(cs[i][0]), (__float_as_uint(cs[i][1]) & ~3u) | (ep1 & 3));
      }
      __syncwarp();
    }
  } else if (warp >= 8) {
    asm volatile("setmaxnreg.dec.sync.aligned.u32 40;");
    if (warp == 8) {
      const bool el = elect_one();
      cluster_wait();
      if (el) {
#pragma unroll 1
        for (int l = 0; l < NLAYERS; l++) {
          const uint32_t par = l & 1;
          const CUtensorMap* tqk = par ? &tm_wf : &tm_wqA;
          const CUtensorMap* tv = par ? &tm_wqB : &tm_wqA;
          const CUtensorMap* two = par ? &tm_woB : &tm_woA;
          if (l == 1) { LOAD_EPOCH(); wait_flag(&g_flags.wfready[jj].v, ep1 * 16); fence_proxy_async_global(); }
#pragma unroll 1
          for (int u = 0; u < 32; u++) {
            if (u >= 4) mbar_wait_sl(bar_done + (u - 4) * 8, par);
            else if (l) mbar_wait_sl(bar_done + (43 + u + (u >> 1)) * 8, par ^ 1);
            else if (u == 1) __nanosleep(STAG1);
            else if (u == 2) mbar_wait_sl(bar_full, 0);
            const uint32_t fb = bar_full + u * 8;
            const bool res = u < 4 ? (l || u >= 2) : (u < 11 || (u >= 18 && u < 22));
            mbar_expect_tx(fb, res ? QST : QST + SLOT);
            const int row = kslice(jj, u < 4 ? u & 1 : (u < 18 ? u - 2 : (u < 22 ? u - 6 : u - 20))) * 64 + (int)rank * 32;
            const int ps = u < 4 ? u >> 1 : (u >= 18), col = jj * 128 + ps * 64;
            const int c0 = par ? jj * 128 + (ps ? 0 : 1024) : col;
            const uint32_t dst = sbase + (u & 3) * QST + rank * 4096;
            tma_load_2d_mc(dst, tqk, fb, c0, row);
            tma_load_2d_mc(dst + 8192, tqk, fb, c0 + (par ? 64 : 1024), row);
            tma_load_2d_mc(dst + 16384, tv, fb, col + 2048, row);
            if (l == 0 && u < 4) PROFT(473 + u);
          }
#pragma unroll 1
          for (int s = 0; s < 16; s++) {
            if (s < 5) { if (s != 2 && s != 4) mbar_wait_sl(bar_done + (28 + s) * 8, par); }
            else if (s != 14) mbar_wait_sl(bar_done + (27 + s - (s == 15)) * 8, par);
            const uint32_t fb = bar_full + (32 + s) * 8;
            mbar_expect_tx(fb, SLOT);
            tma_load_2d_mc(sbase + rank * 8192 + (uint32_t)((WO_BSLOT >> (4 * s)) & 15) * SLOT, two, fb, jj * 128 + (int)rank * 64, wslice(jj, s) * 64);
            const int ts = s + par;
            if (s >= 5 && ts < 8) {
              mbar_expect_tx(bar_chk + 104 + ts * 8, SLOT);
              tma_load_2d(sbase + (uint32_t)((WO_ASLOT(par) >> (4 * ts)) & 15) * SLOT, &tm_o, bar_chk + 104 + ts * 8, wslice(jj, ts) * 64, mm * 128);
            }
          }
        }
      }
      __syncwarp();
    } else if (warp == 9) {
      const bool el = elect_one();
      if (el) {
        PROFT(472);
        tma_load_2d(sbase + OFF_S, &tm_x0, bar_full, jj * 128, mm * 128);
        __nanosleep(STAG1);
        tma_load_2d(sbase + OFF_S + SLOT, &tm_x0, bar_full + 8, jj * 128 + 64, mm * 128);
      }
      __syncwarp();
      LOAD_EPOCH();
#pragma unroll 1
      for (int lp = 0; lp < 4 * NLAYERS; lp++) {
        const int l = lp >> 2, ph = lp & 3;
        if (ph == 3) continue;
        const uint32_t par = l & 1;
        const __nv_bfloat16* pb = g_obuf + (ph >> 1) * 64 + (size_t)(mm * 128 + (ph ? 0 : S_LEN) + (lane & 7) * 16 + (jj & 1) * 8) * D_MODEL + (jj >> 1) * 16;
        const CUtensorMap* tm = lp ? &tm_o : &tm_x0;
        const int row = mm * 128 + ((ph || !l) ? 0 : S_LEN);
        const uint32_t bit = ph ? O_BIT(l) : X_BIT(l - 1);
        const uint32_t slots = ph ? (uint32_t)(WO_ASLOT(par) >> (ph * 32 - 28)) : 0x8769876u;
        const unsigned long long fr = ph == 0 ? 0x06050400000000ull : ph == 1 ? (par ? 0x2120353535351Full : 0x22212035351F1Eull) : (par ? 0x27262524232232ull : 0x27262524233232ull);
        uint32_t rdy = (lp == 0 || (lp & 7) == 1) ? 0xFF : 0;
        mbar_wait_sl(ph ? bar_done + ((uint32_t)fr & 63) * 8 : (l ? bar_done + 47 * 8 : bar_full), ph ? par : (l ? par ^ 1 : 0));
#pragma unroll 1
        for (int i = 0; i < (ph == 1 ? 4 + par : 7); i++) {
          if (!((rdy >> i) & 1) && (i < NPOLL || ph == 1)) {
            const unsigned* pp = reinterpret_cast<const unsigned*>(pb + srcb(jj, i + ((lane >> 3) & (POLLW - 1)), ph) * 128);
            if (i == 0) __nanosleep(POLL0);
            unsigned v0 = ld_relaxed(pp);
            __nanosleep(POLLGAP);
            unsigned v1 = ld_relaxed(pp);
            uint32_t no;
#pragma unroll 1
            for (int it = 0; it < (1 << 18); it++) {
              no = __ballot_sync(0xffffffffu, (v0 ^ bit) & 1);
              if (!(no & 0xFF)) break;
              v0 = ld_relaxed(pp);
              no = __ballot_sync(0xffffffffu, (v1 ^ bit) & 1);
              if (!(no & 0xFF)) break;
              v1 = ld_relaxed(pp);
            }
            rdy = ((1 | (no & 0xFF00 ? 0 : 2) | (no & 0xFF0000 ? 0 : 4) | (no >> 24 ? 0 : 8)) & ((1 << POLLW) - 1)) << i;
          }
          if (ph || i >= 4) mbar_wait_sl(bar_done + ((uint32_t)(fr >> (8 * i)) & 63) * 8, par);
          if (el) {
            if (i == 0) PROFT(320 + l * 16 + ph);
            const uint32_t cb = bar_chk + (ph & 1) * 112 + i * 8;
            mbar_expect_tx(cb, SLOT);
            tma_load_2d(sbase + ((slots >> (4 * i)) & 15) * SLOT, tm, cb, srcb(jj, i, ph) * 128 + (ph >> 1) * 64, row);
          }
          __syncwarp();
        }
        if (ph == 0 && el) {
          if (l) { wait_flag(&g_flags.xready[l][mm].v, ep1 * 8); fence_proxy_async_global(); }
#pragma unroll 1
          for (int u = 11; u < 34; u++) {
            if (u == 18) u = 22;
            mbar_wait_sl(bar_done + (u - 4) * 8, par);
            if (u == 32) mbar_expect_tx(bar_xr, 2 * SLOT);
            tma_load_2d(sbase + OFF_RA + (u & 3) * SLOT, tm, u < 32 ? bar_full + u * 8 : bar_xr, kslice(jj, u < 18 ? u - 2 : (u < 32 ? u - 20 : u - 32)) * 64, row);
          }
        }
        __syncwarp();
      }
      cluster_wait();
    } else {
      const int hw = warp - 10;
      LOAD_EPOCH();
      const bool el = elect_one();
      cluster_wait();
      if (hw == 0) {
        mbar_wait_sl(bar_full + 8, 0);
        if (lane < 7) prefetch_tmap(lane == 0 ? &tm_os : lane == 1 ? &tm_o : lane == 2 ? &tm_wf : lane == 3 ? &tm_wqB : lane == 4 ? &tm_woA : lane == 5 ? &tm_woB : &tm_phi);
        mbar_wait_sl(bar_done + FSTART * 8, 0);
#pragma unroll 1
        for (int i = 0; i < (NLAYERS > 1 ? 9 : 0); i++) {
          if (i > 4) asm volatile("prefetch.global.L2 [%0];" :: "l"(prm.wB_qkv + (size_t)(mm * 64 + (i - 5) * 16 + (lane >> 1)) * 3072 + 1024 + jj * 128 + (lane & 1) * 64));
          else if (el) {
            if (i == 0) { mbar_expect_tx(bar_phi, SLOT + 8192); tma_load_2d(sbase + OFF_PHI, &tm_phi, bar_phi, 0, jj * 128); }
            else tma_load_2d(sbase + 12 * SLOT - 4096 + i * 4096, &tm_wqB, bar_phi, jj * 128 + ((i - 1) >> 1) * 64, mm * 64 + (~i & 1) * 32);
          }
          __syncwarp();
          __nanosleep(PFGAP);
        }
      } else {
#pragma unroll 1
        for (int b = 0; b < 2; b++) {
          float4* z = reinterpret_cast<float4*>(g_kv[b] + (jj * 4) * KVH + mm * (4 * KVH / 16)) + lane;
#pragma unroll
          for (int i = 0; i < 5; i++) z[i * 32] = make_float4(0.f, 0.f, 0.f, 0.f);
        }
#pragma unroll 1
        for (int i = 0; i < 16; i++) {
          const int b = i >> 2;
          const uint32_t v = (b == 0 ? O_BIT(0) : b == 1 ? X_BIT(0) : (NLAYERS > 2 ? 1u : ep1)) + 1;
          uint4* p = b < 2 ? reinterpret_cast<uint4*>(g_obuf + (size_t)(b * S_LEN + mm * 128 + (i & 3) * 32 + (lane >> 3) * 8) * D_MODEL + jj * 128 + (b ? 0 : 64)) + (lane & 7)
                           : g_halo + (size_t)(mm * 8 + jj) * 512 + (i - 8) * 32 + 256 + lane;
          *p = make_uint4(v, v, v, v);
        }
        fence_proxy_async_global();
      }
      __syncwarp();
      uint32_t chkp = 0;
#pragma unroll 1
      for (int lp = 0; lp < 4 * NLAYERS; lp++) {
        const int l = lp >> 2, ph = lp & 3;
        if (ph >= 2 + hw) continue;
        const uint32_t par = l & 1;
        int lane; asm volatile("mov.u32 %0, %%laneid;" : "=r"(lane));
        if (hw) {
          const uint32_t bit = ph ? O_BIT(l) : X_BIT(l - 1);
          const uint32_t slots = ph ? (uint32_t)(WO_ASLOT(par) >> (ph * 32 - 28)) : 0x8769876u;
#pragma unroll 1
          for (int c = 0; c < 7; c++) {
            const uint32_t tile = sbase + ((slots >> (4 * c)) & 15) * SLOT;
            const int cb = c + (ph & 1) * 14;
#pragma unroll 1
            for (int it = 0; it < (1 << 12); it++) {
              mbar_wait_sl(bar_chk + cb * 8, (chkp >> cb) & 1);
              chkp ^= 1u << cb;
              if (el && c == 0) PROFT(ph == 1 ? 480 + l * 2 : 488 + l * 2 + (ph >> 1));
              if (lp == 0) break;
              uint32_t a1 = 1, o1 = 0;
#pragma unroll
              for (int i = 0; i < 16; i++) {
                uint32_t w;
                asm volatile("ld.shared.u32 %0, [%1];" : "=r"(w) : "r"(tile + i * 1024 + (lane & 7) * 132 + (lane >> 3) * 32) : "memory");
                a1 &= w; o1 |= w;
              }
              if (__all_sync(0xffffffffu, ((bit ? a1 : ~o1) & 1) != 0)) break;
              if (el) {
                fence_proxy_async_smem();
                mbar_expect_tx(bar_chk + cb * 8, SLOT);
                tma_load_2d(tile, &tm_o, bar_chk + cb * 8, srcb(jj, c, ph) * 128 + (ph >> 1) * 64, mm * 128 + (ph ? 0 : S_LEN));
                RETRY_COUNT();
              }
              __syncwarp();
            }
            if (el) mbar_arrive_local(bar_full + (c + (ph ? 25 + ph * 8 : 4)) * 8);
            __syncwarp();
          }
          if (ph) continue;
#pragma unroll 1
          for (int hp = 0; hp < 2; hp++) {
            const uint4* src = reinterpret_cast<const uint4*>(g_colsum[par][jj * 64 + hp * 32 + lane]);
            uint32_t bad;
            int it = 0;
            float c[6];
            do {
              bad = 0;
#pragma unroll
              for (int p = 0; p < 3; p++) {
                const uint4 v = ld_ll(src + ((par && p < 2) ? (hp ? -32 : 512) + p * 32 : p * 512));
                bad |= (v.y ^ ep1) | (v.w ^ ep1);
                c[2 * p] = __uint_as_float(v.x) + __uint_as_float(v.z); c[2 * p + 1] = __uint_as_float(v.y) + __uint_as_float(v.w);
              }
              bad &= 3;
              if (bad) __nanosleep(300);
            } while (bad && ++it < (1 << 16));
#pragma unroll
            for (int p = 0; p < 6; p++) {
              uint32_t h, m, lo;
              split3(c[p], h, m, lo);
              sts128(sbase + OFF_LNB + hp * 4096 + (p >> 1) * 1024 + lane * 32 + (p & 1) * 16, h | (m << 16), h | (lo << 16), h | (m << 16), lo | (m << 16));
            }
            fence_proxy_async_smem();
            __syncwarp();
            if (el) { mbar_arrive_local(hp ? bar_stat2 : bar_stat); if (hp == 0) PROFT(324 + l * 16); }
            __syncwarp();
          }
          continue;
        } else if (ph == 0) {
          mbar_wait_sl(bar_done + 24, par);
          const uint4* sp = reinterpret_cast<const uint4*>(g_stats + (size_t)(mm * 128) * 8) + lane;
#pragma unroll 1
          for (int hf = 0; hf < 4; hf++) {
            uint4 v[4];
            uint32_t bad;
            int it = 0;
            do {
              bad = 0;
#pragma unroll
              for (int i = 0; i < 4; i++) { v[i] = ld_ll(sp + (hf * 4 + i) * 32); bad |= (v[i].y ^ STAT_TAG(l)) | (v[i].w ^ STAT_TAG(l)); }
              bad &= 3;
              if (bad) __nanosleep(200);
            } while (bad && ++it < (1 << 16));
            __syncwarp();
            float mean = 0.f, m2 = 0.f;
#pragma unroll
            for (int i = 0; i < 4; i++) {
              float a = __uint_as_float(v[i].x) + __uint_as_float(v[i].z);
              a += __shfl_xor_sync(0xffffffffu, a, 1); a += __shfl_xor_sync(0xffffffffu, a, 2);
              a *= 0.125f;
              const float e0 = __uint_as_float(v[i].x) - a, e1 = __uint_as_float(v[i].z) - a;
              float q = fmaf(fmaf(e0, e0, e1 * e1), 128.f, __uint_as_float(v[i].y) + __uint_as_float(v[i].w));
              q += __shfl_xor_sync(0xffffffffu, q, 1); q += __shfl_xor_sync(0xffffffffu, q, 2);
              if ((lane & 3) == i) { mean = a; m2 = q; }
            }
            const uint32_t row = hf * 32 + (lane & 3) * 8 + (lane >> 2);
            uint32_t h, m, lo;
            split3(-0.5f * mean, h, m, lo);
            sts128(sbase + OFF_LNA + row * 16, h | (h << 16), m | (h << 16), lo | (m << 16), m | (lo << 16));
            sts32f(sbase + OFF_ST + row * 4, rsqrtf(m2 * (1.f / 1024.f) + 1e-5f));
          }
          fence_proxy_async_smem();
          __syncwarp();
          if (el) { mbar_arrive_local(bar_stat); PROFT(323 + l * 16); }
          __syncwarp();
#pragma unroll 1
          for (int i = 0; i < 8 - 4 * l; i++) {
            asm volatile("prefetch.global.L2 [%0];" :: "l"(i < 4 ? (l ? prm.wB_o : prm.wA_o) + (size_t)cta * 8192 + i * 2048 + lane * 64
                                                                 : prm.wB_qkv + (size_t)(cta * 8 + (i - 4) * 2 + (lane >> 4)) * 3072 + 2048 + (lane & 15) * 64));
            __nanosleep(PFGAP);
          }
          continue;
        }
        {
          {
            if (l & 1)
#pragma unroll 1
            for (int h = 0; h < 2; h++) {
              asm volatile("bar.sync %0, 288;" :: "r"(BAR_KV + h) : "memory");
              __syncwarp();
              PROFT(331 + l * 16 + h);
              if (lane < 16) signal_release(&g_flags.kvready[(l & 2) + h][jj][lane].v);
              const unsigned* kf = &g_flags.kvready[(l & 2) + h][jj][mm].v;
              unsigned v0 = ld_relaxed(kf);
              __nanosleep(150);
              unsigned v1 = ld_relaxed(kf);
#pragma unroll 1
              for (int it = 0; it < (1 << 18); it++) {
                if (v0 == ep1 * 16) break;
                v0 = ld_relaxed(kf);
                if (v1 == ep1 * 16) break;
                v1 = ld_relaxed(kf);
              }
              fence_acquire();
              __syncwarp();
              if (h) mbar_wait_sl(bar_lx, 1);
              if (el) {
                PROFT(333 + l * 16 + h);
                fence_proxy_async_global();
                mbar_expect_tx(bar_kvf + h * 8, 2 * KVH * 4);
#pragma unroll 1
                for (int i = 0; i < 4; i++)
                  asm volatile("cp.async.bulk.shared::cluster.global.mbarrier::complete_tx::bytes [%0], [%1], %2, [%3];"
                               :: "r"(sbase + ((i & 1) ? OFF_PHI + h * 4096 + (i >> 1) * 2048 : 11 * SLOT + (i >> 1) * 8192)),
                                  "l"(g_kv[l >> 1] + (jj * 4 + h * 2 + (i >> 1)) * KVH + (i & 1) * 2048), "r"((i & 1) ? 2048 : 8192), "r"(bar_kvf + h * 8) : "memory");
              }
              __syncwarp();
            }
          }
#pragma unroll 1
          for (uint32_t ev = l == NLAYERS - 1 ? 0x8u : (l == 0 ? 0x83654u : 0x83u); ev != 8; ev >>= 4) {
            const int e = ev & 15;
            asm volatile("bar.sync %0, 288;" :: "r"((0xFECA987 >> (4 * e)) & 15) : "memory");
            if (el) {
              if (e < 4) {
                PROFT(325 + l * 16 + e);
                tma_store_2d(&tm_o, sbase + 11 * SLOT, jj * 128 + 64, mm * 128 + S_LEN);
              } else {
                if (e == 5) mbar_expect_tx(bar_phi + 8, SLOT);
#pragma unroll 1
                for (int i = 0; i < 4; i++) {
                  const uint32_t a = sbase + (e > 4 ? 10 : 12) * SLOT + i * 4096;
                  const int c0 = (e > 4 ? 1024 : 0) + jj * 128 + (i >> 1) * 64, c1 = mm * 64 + (i & 1) * 32;
                  if (e == 5) tma_load_2d(a, &tm_wqB, bar_phi + 8, c0, c1); else tma_store_2d(&tm_wf, a, c0, c1);
                }
                if (e != 5) {
                  asm volatile("cp.async.bulk.commit_group;\ncp.async.bulk.wait_group.read 0;" ::: "memory");
                  mbar_arrive_local(bar_phi + (e - 4) * 4);
                }
              }
              if ((0x48 >> e) & 1) {
                bulk_commit_wait();
                signal_release(e == 6 ? &g_flags.wfready[jj].v : &g_flags.xready[l + 1][mm].v);
              }
              if (e == 3) PROFT(330 + l * 16);
              if (e == 6) PROFT(335);
            }
            __syncwarp();
          }
        }
      }
    }
    cluster_sync();
  } else {
    asm volatile("setmaxnreg.inc.sync.aligned.u32 232;");
    LOAD_EPOCH();
    const int wg = warp >> 2;
    const int r0 = warp * 16;
    const uint32_t pK = sbase + OFF_S, pV = sbase + OFF_S + SLOT;
#define PMASKS(on, bit) const uint32_t pm0 = ((on) && t == (g & 3) && (g >> 2) == (g & 1)), pm1 = ((on) && t == (g & 3) && (g >> 2) != (g & 1)), pbit = (bit)
#define PBIT0(w) (((w) & ~pm0) | (pbit & pm0))
#define PBIT1(w) (((w) & ~pm1) | (pbit & pm1))
#define LANE_CONSTS() \
    int lane; asm volatile("mov.u32 %0, %%laneid;" : "=r"(lane)); \
    const int g = lane >> 2, t = lane & 3; \
    const uint32_t srowoff = (r0 + (lane & 15)) * 128, lsw = (lane & 7) << 4, lhi = (lane >> 4) << 4, lsw2 = (lane & 6) << 3; \
    (void)g; (void)t; (void)srowoff; (void)lsw; (void)lhi; (void)lsw2;
    uint32_t stgp = 0, peer;
    asm volatile("mapa.shared::cluster.u32 %0, %1, %2;" : "=r"(peer) : "r"(sbase), "r"(rank ^ 1));
    peer -= sbase;
    const uint32_t dA0 = (((sbase & 0x3FFFF) + wg * 8192) >> 4) | 0x10000u, dB0 = ((sbase & 0x3FFFF) >> 4) | 0x2000000u;
    cluster_wait();
#define DESC(lo, hi) ((uint64_t)(uint32_t)(lo) | ((uint64_t)(hi) << 32))
#define STG_ARRIVE() { __syncwarp(); if (elect_one()) mbar_arrive_local(bar_stg); }
#define STG_WAIT() { mbar_wait(bar_stg, stgp); stgp ^= 1; }
#define PROFS() do {} while (0)
#define REL(addr) { if (elect_one()) { mbar_arrive_local(addr); asm volatile("mbarrier.arrive.shared::cluster.b64 _, [%0];" :: "r"((addr) + peer) : "memory"); } }
#define QSTEP(ACC, DA, SC, PRE) { \
      const uint32_t da = (DA), db = dB0 + (ub & 0x18) * (QST >> 7); \
      mbar_wait(ub, par); \
      PRE; \
      wgmma_fence(); \
      wgmma4_n192<SC>(ACC, da, db); \
      wgmma_commit(); PROFS(); }
#define QREL() { wgmma_wait<1>(); REL(ub + 376); ub += 8; }
#define RA_CUR (dA0 + (OFF_RA >> 4) + (ub & 0x18) * (SLOT >> 7))
#define PUMP1() { QSTEP(S1, RA_CUR, 1, {}); QREL(); }
#define PUMP0() { PUMP1(); SCHED_FENCE(); }
#define PUMP() if (h == 0) PUMP1()
#define WSTEP() { \
      const uint32_t s4 = (ub - bar_full - 256) >> 1; \
      const uint32_t da = dA0 + (((uint32_t)(WO_ASLOT(par) >> s4) & 15) << 10), db = dB0 + (((uint32_t)(WO_BSLOT >> s4) & 15) << 10); \
      mbar_wait(ub, par); \
      wgmma_fence(); \
      wgmma4_n128<1>(S1, da, db); \
      wgmma_commit(); PROFS(); \
      wgmma_wait<1>(); \
      if (s4) REL(ub + 376); \
      ub += 8; }
#define PUMPS(n) { _Pragma("unroll 1") for (int i_ = 0; i_ < (n); i_++) PUMP1(); }
#define SITE(n) { if ((BMASK >> (n)) & 1) PUMP1(); SCHED_FENCE(); }
#define LNSTEP(ACC, hh) { wgmma_fence(); wgmma_n192<1, 0>(ACC, make_desc(sbase + OFF_LNA + wg * 1024, 0, 128) ^ (1ull << 62), make_desc(sbase + OFF_LNB + (hh) * 4096, 0, 128) ^ (1ull << 62)); }
#define DRAIN_A(ACC, PMP) { \
      LANE_CONSTS(); \
      STAGE64(ACC, 64, pV, 1, 1); \
      PMP; \
      STAGE64(ACC, 32, pK, 0, 1); \
      STG_ARRIVE(); \
      _Pragma("unroll") for (int i_ = 0; i_ < 16; i_++) qa[i_] = pack_bf16(ACC[2 * i_], ACC[2 * i_ + 1]); \
      PINU(qa, 16); }
#define DRAIN_B(ACC) { \
      LANE_CONSTS(); \
      STAGE64(ACC, 64, pV, 1, 0); \
      _Pragma("unroll") for (int i_ = 0; i_ < 64; i_++) st[i_] = ACC[i_]; \
      PIN(st, 64); }
#define WARP_STORE(tm, tile, col, row) { fence_proxy_async_smem(); __syncwarp(); \
      if (elect_one()) { tma_store_2d(tm, (tile) + r0 * 128, col, (row) + r0); asm volatile("cp.async.bulk.commit_group;" ::: "memory"); } __syncwarp(); }
#define PUBLISH_O() WARP_STORE(&tm_os, pO, jj * 128 + h * 64, mm * 128)
#define X_OUT(pc, on) { \
      PMASKS(on, X_BIT(l)); \
      _Pragma("unroll") for (int j = (pc) * 4; j < (pc) * 4 + 4; j++) \
        stsm_x4(pK + (pc) * SLOT + srowoff + ((((uint32_t)(j & 3) << 5) + lhi) ^ lsw), \
                PBIT0(pack_bf16(S1[j * 8 + 0], S1[j * 8 + 1])), PBIT0(pack_bf16(S1[j * 8 + 2], S1[j * 8 + 3])), \
                PBIT1(pack_bf16(S1[j * 8 + 4], S1[j * 8 + 5])), PBIT1(pack_bf16(S1[j * 8 + 6], S1[j * 8 + 7]))); }
#define REST_P1(SKEW, HOOK) { \
      mbar_wait(bar_stat2, par); \
      LNSTEP(S1, 1); \
      _Pragma("unroll 1") while (ub < bar_full + 256) { \
        if (ub == bar_full + 256 - 8 * (SKEW) && wg == 0) bar_sync<BAR_SKEW, 256>(); \
        QSTEP(S1, RA_CUR, 1, {}); \
        if (ub == bar_full + 248 && wg == 1) bar_arrive<BAR_SKEW, 256>(); \
        QREL(); \
      } \
      hbase += 256; \
      HOOK; \
      mbar_wait(bar_done + (31 - (SKEW)) * 8, par);        \
      wgmma_wait<0>(); \
      ACC_FENCE(S1, 96); \
      REL(bar_done + 31 * 8); \
      PROF(13); }
#define FOLD(tile, rd) { \
          LANE_CONSTS(); \
          float d[32]; \
          ACC_DEF(d, 32); \
          mbar_wait(bar_phi + (rd) * 8, 0); \
          wgmma_fence(); \
          _Pragma("unroll") for (int i = 0; i < 2; i++) { \
            const uint64_t da = make_desc((tile) + wg * 8192 + i * 64, 16, 1024); \
            const uint64_t db = make_desc(sbase + OFF_PHI + wg * 4096 + i * 2048, 16, 512) ^ (3ull << 62); \
            wgmma_n32<0>(d + i * 16, da, db); wgmma_n32<1>(d + i * 16, da + 2, db + 64); \
          } \
          wgmma_commit(); \
          PUMP0(); \
          ACC_FENCE(d, 32); \
          bar_wg(wg); \
          _Pragma("unroll") for (int i = 0; i < 4; i++) { \
            const float* x = d + (i & 1) * 8 + (i >> 1) * 2; \
            if (rd) sts128((tile) + wg * 8192 + ((warp & 3) * 16 + (i >> 1) * 8 + g) * 128 + (((2 * t + (i & 1)) ^ g) << 4), \
                           pack_bf16(x[0], x[1]), pack_bf16(x[4], x[5]), pack_bf16(x[16], x[17]), pack_bf16(x[20], x[21])); \
            else stsm_x4((tile) + srowoff + ((((uint32_t)i << 5) + lhi) ^ lsw), pack_bf16(d[i * 8], d[i * 8 + 1]), pack_bf16(d[i * 8 + 2], d[i * 8 + 3]), \
                         pack_bf16(d[i * 8 + 4], d[i * 8 + 5]), pack_bf16(d[i * 8 + 6], d[i * 8 + 7])); \
          } \
          fence_proxy_async_smem(); \
          bar_arrive<BAR_WF + 3 * (rd), 288>(); }
#define LOAD_X0(base) \
      _Pragma("unroll") for (int j = 0; j < 8; j++) { \
        uint32_t x0, x1, x2, x3; \
        ldsm_x4((base) + (j >> 2) * SLOT + srowoff + ((((uint32_t)(j & 3) << 5) + lhi) ^ lsw), x0, x1, x2, x3); \
        S1[j * 8 + 0] = bf_lo(x0); S1[j * 8 + 1] = bf_hi(x0); S1[j * 8 + 2] = bf_lo(x1); S1[j * 8 + 3] = bf_hi(x1); \
        S1[j * 8 + 4] = bf_lo(x2); S1[j * 8 + 5] = bf_hi(x2); S1[j * 8 + 6] = bf_lo(x3); S1[j * 8 + 7] = bf_hi(x3); \
      }
#define LOAD_X() { \
      wgmma_wait<0>(); \
      mbar_wait(bar_xr, par); \
      LOAD_X0(sbase + OFF_RA); \
      ACC_FENCE(S1, 64); \
      __syncwarp(); if (elect_one()) mbar_arrive_local(bar_lx); }

    float S1[96];
#pragma unroll
    for (int i = 0; i < 64; i++) S1[i] = 0.f;
#pragma unroll 1
    for (int l = 0; l < NLAYERS; l++) {
      const uint32_t par = l & 1;
      bar_wg(wg);
      PROF(0);
      uint32_t ub = bar_full;
      const bool hsend = (warp == 7) && (mm < 15);
      const uint32_t hbit = (NLAYERS > 2) ? (l == 0) : (ep1 & 1);
      float S0[96];
      {
        LANE_CONSTS();
        ACC_DEF(S0, 96);
        QSTEP(S0, dA0 + (OFF_S >> 4), 0, {});
        ub += 8;
        PROF(1);
        if (l == 0) { mbar_wait(ub, 0); LOAD_X0(pK); }
        else { X_OUT(1, false); fence_proxy_async_smem(); }
        SCHED_FENCE();
        {
          float a0 = S1[0], a1 = S1[2], b0 = S1[1], b1 = S1[3];
#pragma unroll
          for (int i = 4; i < 64; i += 4) { a0 += S1[i]; b0 += S1[i + 1]; a1 += S1[i + 2]; b1 += S1[i + 3]; }
          a0 += b0; a1 += b1;
          a0 += __shfl_xor_sync(0xffffffffu, a0, 1); a1 += __shfl_xor_sync(0xffffffffu, a1, 1);
          a0 += __shfl_xor_sync(0xffffffffu, a0, 2); a1 += __shfl_xor_sync(0xffffffffu, a1, 2);
          a0 *= (1.f / 128.f); a1 *= (1.f / 128.f);
          asm volatile("" : "+f"(a0), "+f"(a1));
          bar_wg(wg);
          QSTEP(S0, dA0 + ((OFF_S + SLOT) >> 4), 1, wgmma_wait<0>());
          REL(ub + 376); ub += 8;
          SCHED_FENCE();
          float q0 = 0.f, q1 = 0.f;
          b0 = 0.f; b1 = 0.f;
#pragma unroll
          for (int i = 0; i < 64; i += 4) {
            const float d0 = S1[i] - a0, d1 = S1[i + 1] - a0, d2 = S1[i + 2] - a1, d3 = S1[i + 3] - a1;
            q0 = fmaf(d0, d0, q0); b0 = fmaf(d1, d1, b0); q1 = fmaf(d2, d2, q1); b1 = fmaf(d3, d3, b1);
          }
          q0 += b0; q1 += b1;
          q0 += __shfl_xor_sync(0xffffffffu, q0, 1); q1 += __shfl_xor_sync(0xffffffffu, q1, 1);
          q0 += __shfl_xor_sync(0xffffffffu, q0, 2); q1 += __shfl_xor_sync(0xffffffffu, q1, 2);
          if (t < 2) st_b64(g_stats + (size_t)(mm * 128 + r0 + g + t * 8) * 8 + jj, __float_as_uint(t ? a1 : a0), (__float_as_uint(t ? q1 : q0) & ~3u) | STAT_TAG(l));
        }
        if (l) { asm volatile("cp.async.bulk.wait_group 0;" ::: "memory"); bar_arrive<BAR_O + 3, 288>(); }
        ACC_DEF(S1, 96);
        QSTEP(S1, dA0 + (OFF_S >> 4), 0, {});
        QREL();
        QSTEP(S1, dA0 + ((OFF_S + SLOT) >> 4), 1, {});
        QREL();
#pragma unroll 1
        for (int i = 0; i < 14; i++) {
          QSTEP(S0, RA_CUR, 1, {});
          if (i == 0) PROF(2);
          QREL();
        }
      }
      LANE_CONSTS();
      uint4* hbase = g_halo + (size_t)(mm * 8 + jj) * 512;
      mbar_wait(bar_stat, par);
      LNSTEP(S0, 0);
      wgmma_commit();
      const float rs0 = lds32f(sbase + OFF_ST + (r0 + g) * 4), rs1 = lds32f(sbase + OFF_ST + (r0 + g + 8) * 4);
      PUMP0();
      ACC_FENCE(S0, 96);
      PROF(3);
      if (!par) {
        constexpr uint32_t par = 0;
        uint32_t qa[16];
        DRAIN_A(S0, PUMP0());
#pragma unroll 1
        for (int h = 0; h < 2; h++) {
          const uint32_t pO = sbase + (h ? 3 : 12) * SLOT;
          PROF(4 + h * 12);
          const bool fold = (l == 0 && h == 0 && NLAYERS > 1);
          if (fold) FOLD(pO, 0) else if (h == 0) PUMPS(HPUMP1);
          LANE_CONSTS();
          uint4 hv[8];
#pragma unroll
          for (int i = 0; i < 8; i++) hv[i] = make_uint4(hbit, 0, 0, 0);
          const bool hrec = (warp == 0 && mm > 0);
          if (hrec) {
#pragma unroll
            for (int i = 0; i < 8; i++) hv[i] = ld_b128(hbase + lane - 8 * 512 + i * 32);
          }
          if (h) { LOAD_X(); _Pragma("unroll 1") for (int i_ = 0; i_ < AW0; i_++) WSTEP(); } else PUMPS(HPUMP2);
          const uint32_t halo = sbase + OFF_HALO;
          STG_WAIT();
          if (warp == 0) {
#pragma unroll 1
            for (int it = 0; it < (1 << 16); it++) {
              uint32_t bad = 0;
#pragma unroll
              for (int i = 0; i < 8; i++) bad |= hv[i].x ^ hbit;
              if (__all_sync(0xffffffffu, (bad & 1) == 0)) break;
#pragma unroll
              for (int i = 0; i < 8; i++) hv[i] = ld_b128(hbase + lane - 8 * 512 + i * 32);
            }
#pragma unroll
            for (int i = 0; i < 8; i++)
              stsm_x4(i < 4 ? halo + srowoff + ((((uint32_t)i << 5) + lhi) ^ lsw)
                            : halo + (srowoff >> 1) + (i >> 1) * 1024 + ((((uint32_t)(i & 1) << 5) + lhi) ^ lsw2), hv[i].x, hv[i].y, hv[i].z, hv[i].w);
            __syncwarp();
          }
          PROF(5 + h * 12);
          const uint32_t kb1 = pK + r0 * 128, vb1 = pV + r0 * 64;
          const uint32_t kb0 = r0 ? kb1 - 2048 : halo, vb0 = r0 ? vb1 - 1024 : halo + 2048;
          const uint32_t vhs = r0 ? 8192 : 1024;
          float s[2][4][4];
          {
            uint32_t kf[2][4][4];
#pragma unroll
            for (int i = 0; i < 8; i++) {
              const int hh = i >> 2, jb = i & 3;
              ldsm_x4(((jb < 2) ? kb0 : kb1) + ((jb & 1) * 8 + (lane & 7)) * 128 + ((hh * 64 + ((lane >> 3) << 4)) ^ lsw), kf[hh][jb][0], kf[hh][jb][1], kf[hh][jb][2], kf[hh][jb][3]);
              s[hh][jb][0] = s[hh][jb][1] = s[hh][jb][2] = s[hh][jb][3] = 0.f;
            }
#pragma unroll
            for (int ks = 0; ks < 2; ks++)
#pragma unroll
              for (int i = 0; i < 8; i++) {
                const int hh = i >> 2, jb = i & 3;
                mma_bf16(s[hh][jb], qa[hh * 8 + ks * 4], qa[hh * 8 + ks * 4 + 1], qa[hh * 8 + ks * 4 + 2], qa[hh * 8 + ks * 4 + 3], kf[hh][jb][ks * 2], kf[hh][jb][ks * 2 + 1]);
              }
          }
          PUMP();
          if (fold) bar_arrive<BAR_WF + 2, 288>();
          PROF(6 + h * 12);
          const bool e = g & 1, hb = (2 * t + (g & 1)) <= g;
          uint32_t vf[2][2][2][4];
#pragma unroll
          for (int i = 0; i < 8; i++) {
            const int hh = i >> 2, ks = (i >> 1) & 1, dp = i & 1;
            ldsm_x4_t((ks ? vb1 + hh * 8192 : vb0 + hh * vhs) + (lane & 15) * 64 + ((dp * 32 + lhi) ^ lsw2), vf[hh][ks][dp][0], vf[hh][ks][dp][1], vf[hh][ks][dp][2], vf[hh][ks][dp][3]);
          }
          float va[2][2], vb[2][2], mx[2][2];
#pragma unroll
          for (int hh = 0; hh < 2; hh++) {
            va[hh][0] = e ? s[hh][1][1] : s[hh][1][0];
            vb[hh][0] = hb ? (e ? s[hh][2][1] : s[hh][2][0]) : (e ? s[hh][0][1] : s[hh][0][0]);
            va[hh][1] = e ? s[hh][2][3] : s[hh][2][2];
            vb[hh][1] = hb ? (e ? s[hh][3][3] : s[hh][3][2]) : (e ? s[hh][1][3] : s[hh][1][2]);
          }
          if (warp == 0 && mm == 0) {
#pragma unroll
            for (int hh = 0; hh < 2; hh++) { va[hh][0] = -INFINITY; if (!hb) { vb[hh][0] = -INFINITY; vb[hh][1] = -INFINITY; } }
          }
#pragma unroll
          for (int i = 0; i < 4; i++) mx[i >> 1][i & 1] = fmaxf(va[i >> 1][i & 1], vb[i >> 1][i & 1]);
#pragma unroll
          for (int o = 1; o <= 2; o <<= 1)
#pragma unroll
            for (int i = 0; i < 4; i++) mx[i >> 1][i & 1] = fmaxf(mx[i >> 1][i & 1], __shfl_xor_sync(0xffffffffu, mx[i >> 1][i & 1], o));
          const float sc0 = rs0 * (0.17677669529663687f * LOG2E), sc1 = rs1 * (0.17677669529663687f * LOG2E);
#pragma unroll
          for (int i = 0; i < 4; i++) {
            const float sc = (i & 1) ? sc1 : sc0, m = mx[i >> 1][i & 1];
            va[i >> 1][i & 1] = ex2((va[i >> 1][i & 1] - m) * sc); vb[i >> 1][i & 1] = ex2((vb[i >> 1][i & 1] - m) * sc);
            mx[i >> 1][i & 1] = va[i >> 1][i & 1] + vb[i >> 1][i & 1];
          }
          if (h == 0 && ASITE) { PIN(&va[0][0], 4); PIN(&vb[0][0], 4); PIN(&mx[0][0], 4); PUMP1(); }
#pragma unroll
          for (int o = 1; o <= 2; o <<= 1)
#pragma unroll
            for (int i = 0; i < 4; i++) mx[i >> 1][i & 1] += __shfl_xor_sync(0xffffffffu, mx[i >> 1][i & 1], o);
          const uint32_t selA = e ? 0x1044 : 0x4410, selB = e ? 0x3244 : 0x4432, selL = hb ? 0x4444 : selB, selH = hb ? selB : 0x4444;
          float o[2][4][4];
          uint32_t pa[2][6];
#pragma unroll
          for (int hh = 0; hh < 2; hh++) {
            const float i0 = rcp_fast(mx[hh][0]), i1 = rcp_fast(mx[hh][1]);
            const uint32_t w0 = pack_bf16(va[hh][0] * i0, vb[hh][0] * i0), w1 = pack_bf16(va[hh][1] * i1, vb[hh][1] * i1);
            pa[hh][0] = __byte_perm(w0, 0, selL); pa[hh][1] = __byte_perm(w0, 0, selA); pa[hh][2] = __byte_perm(w1, 0, selL);
            pa[hh][3] = __byte_perm(w0, 0, selH); pa[hh][4] = __byte_perm(w1, 0, selA); pa[hh][5] = __byte_perm(w1, 0, selH);
#pragma unroll
            for (int dj = 0; dj < 4; dj++) { o[hh][dj][0] = o[hh][dj][1] = o[hh][dj][2] = o[hh][dj][3] = 0.f; }
          }
          PROF(7 + h * 12);
#pragma unroll
          for (int i = 0; i < 8; i++) mma_bf16(o[i >> 2][i & 3], pa[i >> 2][0], 0u, pa[i >> 2][1], pa[i >> 2][2], vf[i >> 2][0][(i >> 1) & 1][(i & 1) * 2], vf[i >> 2][0][(i >> 1) & 1][(i & 1) * 2 + 1]);
#pragma unroll
          for (int i = 0; i < 8; i++) mma_bf16(o[i >> 2][i & 3], pa[i >> 2][3], pa[i >> 2][4], 0u, pa[i >> 2][5], vf[i >> 2][1][(i >> 1) & 1][(i & 1) * 2], vf[i >> 2][1][(i >> 1) & 1][(i & 1) * 2 + 1]);
          if (h == 0) PUMP1() else mbar_wait(bar_done + 30 * 8, par);
          if (fold) mbar_wait(bar_phi, 1);
#pragma unroll
          for (int i = 0; i < 4; i++) {
            const int hh = i >> 1, dp = i & 1;
            PMASKS(true, O_BIT(l));
            stsm_x4(pO + srowoff + ((hh * 64 + dp * 32 + lhi) ^ lsw), PBIT0(pack_bf16(o[hh][dp * 2][0], o[hh][dp * 2][1])), PBIT0(pack_bf16(o[hh][dp * 2][2], o[hh][dp * 2][3])),
                    PBIT1(pack_bf16(o[hh][dp * 2 + 1][0], o[hh][dp * 2 + 1][1])), PBIT1(pack_bf16(o[hh][dp * 2 + 1][2], o[hh][dp * 2 + 1][3])));
          }
          PUBLISH_O();
          PROF(11 + h * 12);
          if (h) break;
          if (fold) { PUMPS(FPUMP); FOLD(pK, 1); }
          REST_P1(ASKEW, asm volatile("cp.async.bulk.wait_group.read 0;" ::: "memory"));
          if (fold) mbar_wait(bar_phi + 8, 1);
          DRAIN_A(S1, {});
        }
      } else {
        constexpr uint32_t par = 1;
        float st[64];
        DRAIN_B(S0);
        if (warp < 2) sts128(sbase + OFF_ONES + warp * 512 + lane * 16, 0x3F803F80u, 0x3F803F80u, 0x3F803F80u, 0x3F803F80u);
        const float c0 = rs0 * LOG2E, c1 = rs1 * LOG2E;
#define KV_MMA(vs) { \
          const uint32_t dp = dA0 + 12 * 1024 - wg * 2560, dv = dA0 + (vs) * 1024 + ((OFF_ONES - (vs) * SLOT - 16) << 12) - wg * (512 << 16); \
          STG_WAIT(); \
          wgmma_fence(); \
          _Pragma("unroll") for (int ks = 0; ks < 8; ks++) { \
            const uint64_t a = DESC(dp + ks * 128, 0x40000040), b = DESC(dv + ks * (64 - (64 << 16)), 0x80000020); \
            if (ks == 0) wgmma_n40<0, 1>(kv, a, b); else wgmma_n40<1, 1>(kv, a, b); } \
          wgmma_commit(); }
#define KV_RED(hp) { \
          float* kvg = g_kv[l >> 1] + (jj * 4 + (hp) * 2 + wg) * KVH + ((warp & 3) * 32 + lane) * 4; \
          _Pragma("unroll") for (int i = 0; i < 4; i++) red_v4(kvg + i * 512, kv[i * 4], kv[i * 4 + 1], kv[i * 4 + 2], kv[i * 4 + 3]); \
          if (t == 0) red_v4(kvg + 2048, kv[16], kv[17], kv[18], kv[19]); \
          bar_arrive<BAR_KV + (hp), 288>(); }
#define KV_TILE(hp) { \
          LANE_CONSTS(); \
          float4 v[5]; \
          mbar_wait(bar_kvf + (hp) * 8, l >> 1); \
          PROF(25 + (hp)); \
          _Pragma("unroll") for (int i = 0; i < 5; i++) \
            asm volatile("ld.shared.v4.f32 {%0, %1, %2, %3}, [%4];" : "=f"(v[i].x), "=f"(v[i].y), "=f"(v[i].z), "=f"(v[i].w) \
                         : "r"(i < 4 ? pV + wg * 8192 + i * 2048 + (warp & 3) * 512 + lane * 16 : sbase + OFF_PHI + (hp) * 4096 + warp * 512 + g * 64) : "memory"); \
          bar_wg(wg); \
          const uint32_t e = lane & 7, jt = ((lane >> 1) & 4) + (e >> 1); \
          const uint32_t row = ((((warp >> 1) ^ wg) & 1) << 5) + ((jt & 1) << 4) + ((warp & 1) << 3) + (jt & 6) + (e & 1); \
          const uint32_t kd = pV + wg * 8192 + row * 128, ksw = (row & 7) << 4; \
          _Pragma("unroll") for (int i = 0; i < 2; i++) { \
            const float4 a = v[i * 2], b = v[i * 2 + 1]; \
            stsm_x4(kd + ((i * 32 + lhi) ^ ksw), pack_bf16(a.x, a.y), pack_bf16(a.z, a.w), pack_bf16(b.x, b.y), pack_bf16(b.z, b.w)); \
          } \
          stsm_x4(kd + ((64u + lhi) ^ ksw), pack_bf16(v[4].x, 1.f), pack_bf16(v[4].z, 1.f), 0u, 0u); }
#pragma unroll 1
        for (int h = 0; h < 2; h++) {
          PROF(4 + h * 2);
          SITE(0);
          LANE_CONSTS();
          const uint32_t dsw = (uint32_t)(g ^ (2 * t)) << 4, dst = ((t & 2) ? pK : sbase + 12 * SLOT) + (r0 + g) * 128;
          float e[16], f[16];
          float mn0 = rmin16(st);
          asm volatile("" : "+f"(mn0)); SCHED_FENCE();
          float sa = exps16(e, st, -c0, mn0 * c0), mx0 = rmax16(st);
          asm volatile("" : "+f"(sa), "+f"(mx0)); PIN(e, 16); SITE(1);
          if (h) STG_WAIT();
          store16(e, sa, dst, dsw, 4);
          float sb = exps16(f, st, c0, -mx0 * c0), mn1 = rmin16(st + 2);
          asm volatile("" : "+f"(sb), "+f"(mn1)); PIN(f, 16); SITE(2);
          store16(f, sb, dst, dsw, 0);
          float sc = exps16(e, st + 2, -c1, mn1 * c1), mx1 = rmax16(st + 2);
          asm volatile("" : "+f"(sc), "+f"(mx1)); PIN(e, 16); SITE(3);
          store16(e, sc, dst + 1024, dsw, 4);
          float sd = exps16(f, st + 2, c1, -mx1 * c1);
          asm volatile("" : "+f"(sd)); PIN(f, 16); SITE(4);
          store16(f, sd, dst + 1024, dsw, 0);
          PROF(5 + h * 2);
          if (h) break;
          {
            float kv[20];
            ACC_DEF(kv, 20);
            fence_proxy_async_smem();
            STG_ARRIVE();
            KV_MMA(11);
            PUMP0();
            ACC_FENCE(kv, 20);
            KV_RED(0);
            STG_ARRIVE();
          }
#pragma unroll
          for (int i = 0; i < 32; i++) st[i] = st[32 + i];
        }
        float mq[8];
        {
          float kv[20];
          mbar_wait(bar_stat2, par);
          LNSTEP(S1, 1);
          ub = bar_full + 240;
          PUMP1();
          if (wg == 0) bar_sync<BAR_SKEW, 256>();
          QSTEP(S1, RA_CUR, 1, {});
          if (wg == 1) bar_arrive<BAR_SKEW, 256>();
          QREL();
          if (KT0) KV_TILE(0);
          mbar_wait(bar_done + 30 * 8, par);
          wgmma_wait<0>();
          ACC_FENCE(S1, 96);
          if (!(RLATE & 2)) REL(bar_done + 31 * 8);
          PROF(13);
          LANE_CONSTS();
          STAGE64(S1, 64, sbase + 3 * SLOT, 1, 0);
          fence_proxy_async_smem();
          STG_ARRIVE();
          if (RLATE & 2) REL(bar_done + 31 * 8);
#pragma unroll
          for (int i = 0; i < 32; i++) st[i] = S1[i];
          PIN(st, 32);
          PROF(16);
          ACC_DEF(kv, 20);
          KV_MMA(3);
          SCHED_FENCE();
          extrema(mq, st, c0, c1);
          PIN(mq, 8);
          SCHED_FENCE();
          wgmma_wait<0>();
          ACC_FENCE(kv, 20);
          KV_RED(1);
          PROF(17);
        }
#pragma unroll 1
        for (int h = 0; h < 2; h++) {
          const uint32_t pO = sbase + (h ? 3 : 8) * SLOT;
          LANE_CONSTS();
          uint32_t fq[32];
          expp16(fq, st, -c0, mq[0], -c1, mq[1]); expp16(fq + 8, st, c0, mq[2], c1, mq[3]); PINU(fq, 16);
          PROF(18 + h * 14);
          if (h) {
            asm volatile("cp.async.bulk.wait_group.read 0;" ::: "memory");
            uint32_t n;
#pragma unroll 1
            while (ub < bar_full + 8 * FILL) {
              int it = 0;
              do {
                asm volatile("{\n.reg .pred p, q;\nsetp.ne.u32 q, %4, 0;\nmbarrier.test_wait.parity.shared::cta.b64 p, [%1], %2;\nand.pred p, p, q;\n"
                             "barrier.red.popc.aligned.u32 %0, %3, 128, p;\n}\n"
                             : "=r"(n) : "r"((warp & 3) ? ub : bar_kvf + 8), "r"((warp & 3) ? par : l >> 1), "r"(2 + wg), "r"((warp & 3) | (uint32_t)(lane == 0)) : "memory");
                n = __shfl_sync(0xffffffffu, n, 0);
              } while (n == 0 && ++it < (1 << 20));
              if (n & 1) break;
              WSTEP();
            }
          }
          if (h || !KT0) {
            KV_TILE(h);
            fence_proxy_async_smem();
            STG_ARRIVE();
          }
          SCHED_FENCE();
          expp16(fq + 16, st + 16, -c0, mq[4], -c1, mq[5]); PINU(fq + 16, 8);
          if (h || !KT0) STG_WAIT();
          wgmma_wait<0>();
          ACC_FENCE(S1, 64);
          PROF(19 + h * 14);
          float o[4][20];
#define O_MMA(hh) { \
            const uint64_t db = make_desc(pV + (hh) * 8192, 16, 1024); \
            ACC_DEF(o[(hh) * 2], 20); ACC_DEF(o[(hh) * 2 + 1], 20); \
            wgmma_fence(); \
            wgmma_n40_rs<0>(o[(hh) * 2], fq + (hh) * 16, db + 256); wgmma_n40_rs<0>(o[(hh) * 2 + 1], fq + (hh) * 16 + 8, db); \
            wgmma_n40_rs<1>(o[(hh) * 2], fq + (hh) * 16 + 4, db + 384); wgmma_n40_rs<1>(o[(hh) * 2 + 1], fq + (hh) * 16 + 12, db + 128); \
            wgmma_commit(); }
          O_MMA(0);
          SCHED_FENCE();
          expp16(fq + 24, st + 16, c0, mq[6], c1, mq[7]); PINU(fq + 24, 8);
          SCHED_FENCE();
          PMASKS(true, O_BIT(l));
#pragma unroll
          for (int hh = 0; hh < 2; hh++) {
            if (hh && !OW) O_MMA(1);
            wgmma_wait<0>();
            ACC_FENCE(o[hh * 2], 20); ACC_FENCE(o[hh * 2 + 1], 20);
            if (!hh && OW) { O_MMA(1); SCHED_FENCE(); }
            const float* x = o[hh * 2];
            const float* y = o[hh * 2 + 1];
            const float rx0 = rcp_fast(x[17]), ry0 = rcp_fast(y[17]), rx1 = rcp_fast(x[19]), ry1 = rcp_fast(y[19]);
            const float i0 = rcp_fast(fmaf(x[16], rx0, y[16] * ry0) + 1e-6f), i1 = rcp_fast(fmaf(x[18], rx1, y[18] * ry1) + 1e-6f);
            const float ax0 = rx0 * i0, ay0 = ry0 * i0, ax1 = rx1 * i1, ay1 = ry1 * i1;
#pragma unroll
            for (int dp = 0; dp < 2; dp++)
              stsm_x4(pO + srowoff + ((hh * 64 + dp * 32 + lhi) ^ lsw),
                      PBIT0(pack_bf16(fmaf(x[dp * 8], ax0, y[dp * 8] * ay0), fmaf(x[dp * 8 + 1], ax0, y[dp * 8 + 1] * ay0))),
                      PBIT0(pack_bf16(fmaf(x[dp * 8 + 2], ax1, y[dp * 8 + 2] * ay1), fmaf(x[dp * 8 + 3], ax1, y[dp * 8 + 3] * ay1))),
                      PBIT1(pack_bf16(fmaf(x[dp * 8 + 4], ax0, y[dp * 8 + 4] * ay0), fmaf(x[dp * 8 + 5], ax0, y[dp * 8 + 5] * ay0))),
                      PBIT1(pack_bf16(fmaf(x[dp * 8 + 6], ax1, y[dp * 8 + 6] * ay1), fmaf(x[dp * 8 + 7], ax1, y[dp * 8 + 7] * ay1))));
          }
          PUBLISH_O();
          PROF(20 + h * 14);
          if (h) break;
#pragma unroll
          for (int i = 0; i < 32; i++) st[i] = S1[32 + i];
          PIN(st, 32);
          LOAD_X();
          bar_wg(wg);
          WSTEP();
          SCHED_FENCE();
          extrema(mq, st, c0, c1);
          PIN(mq, 8);
          PROF(31);
        }
      }
      __syncwarp();
      if (elect_one()) mbar_arrive_local(bar_epi);
      bar_wg(wg);
#pragma unroll 1
      while (ub < bar_full + 384) {
        WSTEP();
        if (ub == bar_full + 8 * 41) { asm volatile("cp.async.bulk.wait_group.read 0;" ::: "memory"); PROF(35); }
        if (ub == bar_full + 8 * 42) PROF(36);
      }
      wgmma_wait<0>();
      ACC_FENCE(S1, 64);
      if (!RLATE) REL(bar_done + 47 * 8);
      PROF(37);
      {
        LANE_CONSTS();
        X_OUT(0, l < NLAYERS - 1);
        WARP_STORE(l < NLAYERS - 1 ? &tm_os : &tm_xo, pK, jj * 128, mm * 128 + (l < NLAYERS - 1 ? S_LEN : 0));
        if (RLATE) REL(bar_done + 47 * 8);
        if (l == NLAYERS - 1) {
          X_OUT(1, false);
          WARP_STORE(&tm_xo, pV, jj * 128 + 64, mm * 128);
          asm volatile("cp.async.bulk.wait_group 0;" ::: "memory");
        }
      }
#pragma unroll
      for (int i = 32; i < 64; i++) { uint32_t c; asm volatile("mov.b32 %0, %1;" : "=r"(c) : "f"(S1[i])); S1[i] = __uint_as_float(c); }
      PROF(38);
    }
    const int tid = threadIdx.x;
    if (tid == 0) {
      unsigned old = atomicAdd(&g_flags.done.v, 1);
      if (old == ep1 * NMAIN - 1) {
        asm volatile("st.relaxed.gpu.global.u32 [%0], %1;" :: "l"(&g_flags.epoch.v), "r"(ep1) : "memory");
      }
    }
    __syncwarp();
    cluster_sync();
  }
}

typedef CUresult (*PFN_encode)(CUtensorMap*, CUtensorMapDataType, cuuint32_t, void*, const cuuint64_t*, const cuuint64_t*,
                               const cuuint32_t*, const cuuint32_t*, CUtensorMapInterleave, CUtensorMapSwizzle,
                               CUtensorMapL2promotion, CUtensorMapFloatOOBfill);

CUtensorMap make_map(PFN_encode enc, const void* ptr, uint64_t inner, uint64_t outer, uint32_t box_inner, uint32_t box_outer,
                     CUtensorMapSwizzle swz = CU_TENSOR_MAP_SWIZZLE_128B) {
  CUtensorMap m;
  cuuint64_t dims[2] = {inner, outer};
  cuuint64_t strides[1] = {inner * 2};
  cuuint32_t box[2] = {box_inner, box_outer};
  cuuint32_t es[2] = {1, 1};
  enc(&m, CU_TENSOR_MAP_DATA_TYPE_BFLOAT16, 2, const_cast<void*>(ptr), dims, strides, box, es, CU_TENSOR_MAP_INTERLEAVE_NONE,
      swz, CU_TENSOR_MAP_L2_PROMOTION_L2_256B, CU_TENSOR_MAP_FLOAT_OOB_FILL_NONE);
  return m;
}

}

extern "C" void kernel_launch(void* const* d_in, const int* in_sizes, int n_in, void* d_out, int out_size) {
  (void)in_sizes; (void)n_in; (void)out_size;
  static PFN_encode enc = nullptr;
  if (!enc) {
    void* fn = nullptr;
    cudaDriverEntryPointQueryResult qr;
    cudaGetDriverEntryPoint("cuTensorMapEncodeTiled", &fn, cudaEnableDefault, &qr);
    enc = (PFN_encode)fn;
    cudaFuncSetAttribute(mega_kernel, cudaFuncAttributeMaxDynamicSharedMemorySize, SMEM_BYTES);
  }
  Params prm;
  prm.x0 = (const __nv_bfloat16*)d_in[0];
  prm.wA_qkv = (const __nv_bfloat16*)d_in[1];
  prm.wA_o = (const __nv_bfloat16*)d_in[2];
  prm.wB_qkv = (const __nv_bfloat16*)d_in[4];
  prm.wB_phi = (const __nv_bfloat16*)d_in[5];
  prm.wB_o = (const __nv_bfloat16*)d_in[6];
  prm.out = (__nv_bfloat16*)d_out;
  void *obuf = nullptr, *wf = nullptr;
  cudaGetSymbolAddress(&obuf, g_obuf);
  cudaGetSymbolAddress(&wf, g_wfold);
  CUtensorMap tm_x0 = make_map(enc, d_in[0], D_MODEL, S_LEN, 64, 128);
  CUtensorMap tm_xo = make_map(enc, d_out, D_MODEL, S_LEN, 64, 16);
  CUtensorMap tm_os = make_map(enc, obuf, D_MODEL, 2 * S_LEN, 64, 16);
  CUtensorMap tm_o = make_map(enc, obuf, D_MODEL, 2 * S_LEN, 64, 128);
  CUtensorMap tm_wf = make_map(enc, wf, 2048, D_MODEL, 64, 32);
  CUtensorMap tm_wqA = make_map(enc, d_in[1], 3 * D_MODEL, D_MODEL, 64, 32);
  CUtensorMap tm_wqB = make_map(enc, prm.wB_qkv, 3 * D_MODEL, D_MODEL, 64, 32);
  CUtensorMap tm_woA = make_map(enc, prm.wA_o, D_MODEL, D_MODEL, 64, 64);
  CUtensorMap tm_woB = make_map(enc, prm.wB_o, D_MODEL, D_MODEL, 64, 64);
  CUtensorMap tm_phi = make_map(enc, prm.wB_phi, 32, 1024, 32, 128, CU_TENSOR_MAP_SWIZZLE_64B);
  mega_kernel<<<NMAIN + NAUX, 384, SMEM_BYTES>>>(tm_x0, tm_xo, tm_os, tm_o, tm_wf, tm_wqA, tm_wqB, tm_woA, tm_woB, tm_phi, prm);
}
```

```cpp
#include <cuda_runtime.h>
#include <cuda.h>
#include <cuda_bf16.h>
#include <stdint.h>

#define NLAYERS 4

#define STAG1 300
#define HPUMP1 2
#define HPUMP2 1
#define ASKEW 2
#define FPUMP 3
#define PFGAP 100
#define POLLW 4
#define POLL0 0
#define POLLGAP 120
#define OW 1
#define KT0 1
#define NPOLL 4
#define AW0 1
#define RLATE 3
#define FSTART 0
#define MAPV 1
#define ORD 15
#define HW1 29
#define XPACE 0x06050401000000ull
#define XP0 4
#define HW0 18
#define XD 4
#define WFGAP 50
#define FILL 40
#define BMASK 0x1F
#define ASITE 1
namespace {

constexpr int S_LEN = 2048, D_MODEL = 1024;
constexpr int NAUX = 4, NMAIN = 128;
constexpr int SLOT = 16384;
constexpr int QST = 24576;
constexpr int OFF_RA = 6 * SLOT, OFF_S = 10 * SLOT;
constexpr int OFF_HALO = 13 * SLOT, OFF_LNB = OFF_HALO  , OFF_ONES = OFF_HALO + 3072;
constexpr int OFF_ST = OFF_HALO + 7168  , OFF_PHI = OFF_HALO + 8192;
constexpr int OFF_BAR = 14 * SLOT;
constexpr int OFF_LNA = OFF_BAR + 1024;
constexpr int SMEM_BYTES = OFF_LNA + 2048;
#define WO_ASLOT(par) ((par) ? 0x9876CAB39876CA98ull : 0x98C76BA398C7698Cull)
constexpr unsigned long long WO_BSLOT = 0x5432105421054210ull;
__device__ __forceinline__ int srcb(int j, int i, int ph) { return ((ORD >> ph) & 1) ? (i + (i >= j)) & 7 : (j + i + 1) & 7; }
__device__ __forceinline__ int kslice(int j, int i) { return i < 2 ? 2 * j + i : (i < 9 ? 2 * srcb(j, i - 2, 0) : 2 * srcb(j, i - 9, 3) + 1); }
__device__ __forceinline__ int wslice(int j, int s) { return 2 * ((s & 7) ? srcb(j, (s & 7) - 1, 1 + (s >> 3)) : j) + (s >> 3); }
constexpr int KVH = 5 * 128 * 4;

struct __align__(128) Flag { unsigned v; unsigned pad[31]; };
struct Flags {
  Flag xready[4][16];
  Flag kvready[4][8][16];
  Flag wfready[8];
  Flag done;
  Flag epoch;
};

__device__ Flags g_flags;
__device__ __nv_bfloat16 g_obuf[2 * S_LEN * D_MODEL];
#define O_BIT(l) ((epoch * NLAYERS + (l) + 1) & 1u)
#define X_BIT(l) ((epoch * (NLAYERS - 1) + (l) + 1) & 1u)
__device__ __nv_bfloat16 g_wfold[D_MODEL * 2048];
__device__ uint4 g_halo[16 * 8 * 512];
__device__ float g_kv[2][32 * KVH];
__device__ __align__(128) uint2 g_colsum[2][1536][2];
__device__ __align__(128) uint2 g_stats[S_LEN * 8];
#define H_BIT(l) (NLAYERS > 2 ? (uint32_t)((l) == 0) : (ep1 & 1))
#define STAT_TAG(l) ((ep1 * NLAYERS + (l) + 1) & 3u)

#define RETRY_COUNT()
#define PRL 0
#define PRU 0
#define PROFL 1
#define PROFW 0
#define KVFLAG 1
#define PROFT(i) do {} while (0)
#define PROF(i) do {} while (0)

__device__ __forceinline__ uint32_t smem_u32(const void* p) { return (uint32_t)__cvta_generic_to_shared(p); }
__device__ __forceinline__ bool elect_one() {
  uint32_t p;
  asm volatile("{\n.reg .pred p;\nelect.sync _|p, 0xffffffff;\nselp.u32 %0, 1, 0, p;\n}\n" : "=r"(p));
  return p != 0;
}
__device__ __forceinline__ void mbar_init(uint32_t bar, uint32_t cnt) {
  asm volatile("mbarrier.init.shared::cta.b64 [%0], %1;" :: "r"(bar), "r"(cnt));
}
__device__ __forceinline__ void mbar_expect_tx(uint32_t bar, uint32_t bytes) {
  asm volatile("mbarrier.arrive.expect_tx.shared::cta.b64 _, [%0], %1;" :: "r"(bar), "r"(bytes) : "memory");
}
#define mbar_wait(bar, parity) \
  asm volatile("{\n.reg .pred p, q;\nW_%=:\nmbarrier.try_wait.parity.shared::cta.b64 p, [%1], %2;\nadd.s32 %0, %0, -1;\n" \
               "setp.gt.and.s32 q, %0, 0, !p;\n@q bra.uni W_%=;\n}\n" : "+r"(budget) : "r"((uint32_t)(bar)), "r"((uint32_t)(parity)) : "memory")
#define mbar_wait_sl(bar, parity) \
  asm volatile("{\n.reg .pred p, q;\nW_%=:\nmbarrier.try_wait.parity.shared::cta.b64 p, [%1], %2, 20000;\nadd.s32 %0, %0, -64;\n" \
               "setp.gt.and.s32 q, %0, 0, !p;\n@q bra.uni W_%=;\n}\n" : "+r"(budget) : "r"((uint32_t)(bar)), "r"((uint32_t)(parity)) : "memory")
__device__ __forceinline__ void mbar_arrive_local(uint32_t bar) {
  asm volatile("mbarrier.arrive.shared::cta.b64 _, [%0];" :: "r"(bar) : "memory");
}
__device__ __forceinline__ void tma_load_2d(uint32_t dst, const CUtensorMap* tm, uint32_t bar, int c0, int c1) {
  asm volatile("cp.async.bulk.tensor.2d.shared::cluster.global.mbarrier::complete_tx::bytes [%0], [%1, {%3, %4}], [%2];"
               :: "r"(dst), "l"(tm), "r"(bar), "r"(c0), "r"(c1) : "memory");
}
__device__ __forceinline__ void tma_load_2d_mc(uint32_t dst, const CUtensorMap* tm, uint32_t bar, int c0, int c1) {
  asm volatile("cp.async.bulk.tensor.2d.shared::cluster.global.mbarrier::complete_tx::bytes.multicast::cluster [%0], [%1, {%3, %4}], [%2], %5;"
               :: "r"(dst), "l"(tm), "r"(bar), "r"(c0), "r"(c1), "h"((uint16_t)3) : "memory");
}
__device__ __forceinline__ void tma_store_2d(const CUtensorMap* tm, uint32_t src, int c0, int c1) {
  asm volatile("cp.async.bulk.tensor.2d.global.shared::cta.bulk_group [%0, {%2, %3}], [%1];"
               :: "l"(tm), "r"(src), "r"(c0), "r"(c1) : "memory");
}
__device__ __forceinline__ void bulk_commit_wait() {
  asm volatile("cp.async.bulk.commit_group;\ncp.async.bulk.wait_group 0;" ::: "memory");
}
__device__ __forceinline__ void prefetch_tmap(const CUtensorMap* tm) {
  asm volatile("prefetch.tensormap [%0];" :: "l"(tm) : "memory");
}
__device__ __forceinline__ void fence_proxy_async_global() { asm volatile("fence.proxy.async.global;" ::: "memory"); }
__device__ __forceinline__ void fence_proxy_async_smem() { asm volatile("fence.proxy.async.shared::cta;" ::: "memory"); }
__device__ __forceinline__ unsigned ld_relaxed(const unsigned* p) {
  unsigned v;
  asm volatile("ld.relaxed.gpu.global.u32 %0, [%1];" : "=r"(v) : "l"(p) : "memory");
  return v;
}
__device__ __forceinline__ void fence_acquire() { asm volatile("fence.acquire.gpu;" ::: "memory"); }
__device__ __forceinline__ void wait_flag(const unsigned* p, unsigned target) {
  int it = 0;
  while ((int)(ld_relaxed(p) - target) < 0 && ++it < (1 << 20)) {}
  fence_acquire();
}
__device__ __forceinline__ void signal_release(unsigned* p) {
  asm volatile("red.release.gpu.global.add.u32 [%0], 1;" :: "l"(p) : "memory");
}
template <int ID, int N> __device__ __forceinline__ void bar_arrive() { asm volatile("bar.arrive %0, %1;" :: "n"(ID), "n"(N) : "memory"); }
template <int ID, int N> __device__ __forceinline__ void bar_sync() { asm volatile("bar.sync %0, %1;" :: "n"(ID), "n"(N) : "memory"); }
__device__ __forceinline__ void bar_wg(int wg) { asm volatile("bar.sync %0, 128;" :: "r"(2 + wg) : "memory"); }
__device__ __forceinline__ void cluster_sync() {
  asm volatile("barrier.cluster.arrive.relaxed.aligned;\nbarrier.cluster.wait.aligned;" ::: "memory");
}
__device__ __forceinline__ void cluster_wait() { asm volatile("barrier.cluster.wait.acquire.aligned;" ::: "memory"); }
enum { BAR_KV = 4  , BAR_X1 = 7, BAR_WF = 8  , BAR_SKEW = 10 };

__device__ __forceinline__ void wgmma_fence() { asm volatile("wgmma.fence.sync.aligned;" ::: "memory"); }
__device__ __forceinline__ void wgmma_commit() { asm volatile("wgmma.commit_group.sync.aligned;" ::: "memory"); }
template <int N> __device__ __forceinline__ void wgmma_wait() { asm volatile("wgmma.wait_group.sync.aligned %0;" :: "n"(N) : "memory"); }

template <int scale_d, int tnsp_b = 1> __device__ __forceinline__ void wgmma_n192(float* d, uint64_t descA, uint64_t descB) {
  asm volatile("{\n.reg .pred p;\nsetp.ne.b32 p, %98, 0;\n"
               "wgmma.mma_async.sync.aligned.m64n192k16.f32.bf16.bf16 {%0,%1,%2,%3,%4,%5,%6,%7,%8,%9,%10,%11,%12,%13,%14,%15,%16,%17,%18,%19,%20,%21,%22,%23,%24,%25,%26,%27,%28,%29,%30,%31,%32,%33,%34,%35,%36,%37,%38,%39,%40,%41,%42,%43,%44,%45,%46,%47,%48,%49,%50,%51,%52,%53,%54,%55,%56,%57,%58,%59,%60,%61,%62,%63,%64,%65,%66,%67,%68,%69,%70,%71,%72,%73,%74,%75,%76,%77,%78,%79,%80,%81,%82,%83,%84,%85,%86,%87,%88,%89,%90,%91,%92,%93,%94,%95}, %96, %97, p, 1, 1, 0, %99;\n}\n"
               : "+f"(d[0]), "+f"(d[1]), "+f"(d[2]), "+f"(d[3]), "+f"(d[4]), "+f"(d[5]), "+f"(d[6]), "+f"(d[7]), "+f"(d[8]), "+f"(d[9]), "+f"(d[10]), "+f"(d[11]), "+f"(d[12]), "+f"(d[13]), "+f"(d[14]), "+f"(d[15]), "+f"(d[16]), "+f"(d[17]), "+f"(d[18]), "+f"(d[19]), "+f"(d[20]), "+f"(d[21]), "+f"(d[22]), "+f"(d[23]), "+f"(d[24]), "+f"(d[25]), "+f"(d[26]), "+f"(d[27]), "+f"(d[28]), "+f"(d[29]), "+f"(d[30]), "+f"(d[31]), "+f"(d[32]), "+f"(d[33]), "+f"(d[34]), "+f"(d[35]), "+f"(d[36]), "+f"(d[37]), "+f"(d[38]), "+f"(d[39]), "+f"(d[40]), "+f"(d[41]), "+f"(d[42]), "+f"(d[43]), "+f"(d[44]), "+f"(d[45]), "+f"(d[46]), "+f"(d[47]), "+f"(d[48]), "+f"(d[49]), "+f"(d[50]), "+f"(d[51]), "+f"(d[52]), "+f"(d[53]), "+f"(d[54]), "+f"(d[55]), "+f"(d[56]), "+f"(d[57]), "+f"(d[58]), "+f"(d[59]), "+f"(d[60]), "+f"(d[61]), "+f"(d[62]), "+f"(d[63]), "+f"(d[64]), "+f"(d[65]), "+f"(d[66]), "+f"(d[67]), "+f"(d[68]), "+f"(d[69]), "+f"(d[70]), "+f"(d[71]), "+f"(d[72]), "+f"(d[73]), "+f"(d[74]), "+f"(d[75]), "+f"(d[76]), "+f"(d[77]), "+f"(d[78]), "+f"(d[79]), "+f"(d[80]), "+f"(d[81]), "+f"(d[82]), "+f"(d[83]), "+f"(d[84]), "+f"(d[85]), "+f"(d[86]), "+f"(d[87]), "+f"(d[88]), "+f"(d[89]), "+f"(d[90]), "+f"(d[91]), "+f"(d[92]), "+f"(d[93]), "+f"(d[94]), "+f"(d[95])
               : "l"(descA), "l"(descB), "n"(scale_d), "n"(tnsp_b));
}
template <int scale_d> __device__ __forceinline__ void wgmma4_n192(float* d, uint32_t da, uint32_t db) {
#define R_ "{%0,%1,%2,%3,%4,%5,%6,%7,%8,%9,%10,%11,%12,%13,%14,%15,%16,%17,%18,%19,%20,%21,%22,%23,%24,%25,%26,%27,%28,%29,%30,%31,%32,%33,%34,%35,%36,%37,%38,%39,%40,%41,%42,%43,%44,%45,%46,%47,%48,%49,%50,%51,%52,%53,%54,%55,%56,%57,%58,%59,%60,%61,%62,%63,%64,%65,%66,%67,%68,%69,%70,%71,%72,%73,%74,%75,%76,%77,%78,%79,%80,%81,%82,%83,%84,%85,%86,%87,%88,%89,%90,%91,%92,%93,%94,%95}"
  asm volatile("{\n.reg .pred p, q;\n.reg .b64 a, b;\nsetp.ne.b32 p, %98, 0;\nsetp.eq.b32 q, 0, 0;\nmov.b64 a, {%96, 0x40000040};\nmov.b64 b, {%97, 0x40000040};\n"
               "wgmma.mma_async.sync.aligned.m64n192k16.f32.bf16.bf16 " R_ ", a, b, p, 1, 1, 0, 1;\nadd.s64 a, a, 2;\nadd.s64 b, b, 128;\n"
               "wgmma.mma_async.sync.aligned.m64n192k16.f32.bf16.bf16 " R_ ", a, b, q, 1, 1, 0, 1;\nadd.s64 a, a, 2;\nadd.s64 b, b, 128;\n"
               "wgmma.mma_async.sync.aligned.m64n192k16.f32.bf16.bf16 " R_ ", a, b, q, 1, 1, 0, 1;\nadd.s64 a, a, 2;\nadd.s64 b, b, 128;\n"
               "wgmma.mma_async.sync.aligned.m64n192k16.f32.bf16.bf16 " R_ ", a, b, q, 1, 1, 0, 1;\n}\n"
               : "+f"(d[0]), "+f"(d[1]), "+f"(d[2]), "+f"(d[3]), "+f"(d[4]), "+f"(d[5]), "+f"(d[6]), "+f"(d[7]), "+f"(d[8]), "+f"(d[9]), "+f"(d[10]), "+f"(d[11]), "+f"(d[12]), "+f"(d[13]), "+f"(d[14]), "+f"(d[15]), "+f"(d[16]), "+f"(d[17]), "+f"(d[18]), "+f"(d[19]), "+f"(d[20]), "+f"(d[21]), "+f"(d[22]), "+f"(d[23]), "+f"(d[24]), "+f"(d[25]), "+f"(d[26]), "+f"(d[27]), "+f"(d[28]), "+f"(d[29]), "+f"(d[30]), "+f"(d[31]), "+f"(d[32]), "+f"(d[33]), "+f"(d[34]), "+f"(d[35]), "+f"(d[36]), "+f"(d[37]), "+f"(d[38]), "+f"(d[39]), "+f"(d[40]), "+f"(d[41]), "+f"(d[42]), "+f"(d[43]), "+f"(d[44]), "+f"(d[45]), "+f"(d[46]), "+f"(d[47]), "+f"(d[48]), "+f"(d[49]), "+f"(d[50]), "+f"(d[51]), "+f"(d[52]), "+f"(d[53]), "+f"(d[54]), "+f"(d[55]), "+f"(d[56]), "+f"(d[57]), "+f"(d[58]), "+f"(d[59]), "+f"(d[60]), "+f"(d[61]), "+f"(d[62]), "+f"(d[63]), "+f"(d[64]), "+f"(d[65]), "+f"(d[66]), "+f"(d[67]), "+f"(d[68]), "+f"(d[69]), "+f"(d[70]), "+f"(d[71]), "+f"(d[72]), "+f"(d[73]), "+f"(d[74]), "+f"(d[75]), "+f"(d[76]), "+f"(d[77]), "+f"(d[78]), "+f"(d[79]), "+f"(d[80]), "+f"(d[81]), "+f"(d[82]), "+f"(d[83]), "+f"(d[84]), "+f"(d[85]), "+f"(d[86]), "+f"(d[87]), "+f"(d[88]), "+f"(d[89]), "+f"(d[90]), "+f"(d[91]), "+f"(d[92]), "+f"(d[93]), "+f"(d[94]), "+f"(d[95])
               : "r"(da), "r"(db), "n"(scale_d));
#undef R_
}
template <int scale_d> __device__ __forceinline__ void wgmma4_n128(float* d, uint32_t da, uint32_t db) {
#define R_ "{%0,%1,%2,%3,%4,%5,%6,%7,%8,%9,%10,%11,%12,%13,%14,%15,%16,%17,%18,%19,%20,%21,%22,%23,%24,%25,%26,%27,%28,%29,%30,%31,%32,%33,%34,%35,%36,%37,%38,%39,%40,%41,%42,%43,%44,%45,%46,%47,%48,%49,%50,%51,%52,%53,%54,%55,%56,%57,%58,%59,%60,%61,%62,%63}"
  asm volatile("{\n.reg .pred p, q;\n.reg .b64 a, b;\nsetp.ne.b32 p, %66, 0;\nsetp.eq.b32 q, 0, 0;\nmov.b64 a, {%64, 0x40000040};\nmov.b64 b, {%65, 0x40000040};\n"
               "wgmma.mma_async.sync.aligned.m64n128k16.f32.bf16.bf16 " R_ ", a, b, p, 1, 1, 0, 1;\nadd.s64 a, a, 2;\nadd.s64 b, b, 128;\n"
               "wgmma.mma_async.sync.aligned.m64n128k16.f32.bf16.bf16 " R_ ", a, b, q, 1, 1, 0, 1;\nadd.s64 a, a, 2;\nadd.s64 b, b, 128;\n"
               "wgmma.mma_async.sync.aligned.m64n128k16.f32.bf16.bf16 " R_ ", a, b, q, 1, 1, 0, 1;\nadd.s64 a, a, 2;\nadd.s64 b, b, 128;\n"
               "wgmma.mma_async.sync.aligned.m64n128k16.f32.bf16.bf16 " R_ ", a, b, q, 1, 1, 0, 1;\n}\n"
               : "+f"(d[0]), "+f"(d[1]), "+f"(d[2]), "+f"(d[3]), "+f"(d[4]), "+f"(d[5]), "+f"(d[6]), "+f"(d[7]), "+f"(d[8]), "+f"(d[9]), "+f"(d[10]), "+f"(d[11]), "+f"(d[12]), "+f"(d[13]), "+f"(d[14]), "+f"(d[15]), "+f"(d[16]), "+f"(d[17]), "+f"(d[18]), "+f"(d[19]), "+f"(d[20]), "+f"(d[21]), "+f"(d[22]), "+f"(d[23]), "+f"(d[24]), "+f"(d[25]), "+f"(d[26]), "+f"(d[27]), "+f"(d[28]), "+f"(d[29]), "+f"(d[30]), "+f"(d[31]), "+f"(d[32]), "+f"(d[33]), "+f"(d[34]), "+f"(d[35]), "+f"(d[36]), "+f"(d[37]), "+f"(d[38]), "+f"(d[39]), "+f"(d[40]), "+f"(d[41]), "+f"(d[42]), "+f"(d[43]), "+f"(d[44]), "+f"(d[45]), "+f"(d[46]), "+f"(d[47]), "+f"(d[48]), "+f"(d[49]), "+f"(d[50]), "+f"(d[51]), "+f"(d[52]), "+f"(d[53]), "+f"(d[54]), "+f"(d[55]), "+f"(d[56]), "+f"(d[57]), "+f"(d[58]), "+f"(d[59]), "+f"(d[60]), "+f"(d[61]), "+f"(d[62]), "+f"(d[63])
               : "r"(da), "r"(db), "n"(scale_d));
#undef R_
}
template <int scale_d> __device__ __forceinline__ void wgmma_n32(float* d, uint64_t descA, uint64_t descB) {
  asm volatile("{\n.reg .pred p;\nsetp.ne.b32 p, %18, 0;\n"
               "wgmma.mma_async.sync.aligned.m64n32k16.f32.bf16.bf16 {%0,%1,%2,%3,%4,%5,%6,%7,%8,%9,%10,%11,%12,%13,%14,%15}, %16, %17, p, 1, 1, 0, 1;\n}\n"
               : "+f"(d[0]), "+f"(d[1]), "+f"(d[2]), "+f"(d[3]), "+f"(d[4]), "+f"(d[5]), "+f"(d[6]), "+f"(d[7]), "+f"(d[8]), "+f"(d[9]), "+f"(d[10]), "+f"(d[11]), "+f"(d[12]), "+f"(d[13]), "+f"(d[14]), "+f"(d[15])
               : "l"(descA), "l"(descB), "n"(scale_d));
}
template <int scale_d, int tnsp_a> __device__ __forceinline__ void wgmma_n40(float* d, uint64_t descA, uint64_t descB) {
  asm volatile("{\n.reg .pred p;\nsetp.ne.b32 p, %22, 0;\n"
               "wgmma.mma_async.sync.aligned.m64n40k16.f32.bf16.bf16 {%0,%1,%2,%3,%4,%5,%6,%7,%8,%9,%10,%11,%12,%13,%14,%15,%16,%17,%18,%19}, %20, %21, p, 1, 1, %23, 1;\n}\n"
               : "+f"(d[0]), "+f"(d[1]), "+f"(d[2]), "+f"(d[3]), "+f"(d[4]), "+f"(d[5]), "+f"(d[6]), "+f"(d[7]), "+f"(d[8]), "+f"(d[9]), "+f"(d[10]), "+f"(d[11]), "+f"(d[12]), "+f"(d[13]), "+f"(d[14]), "+f"(d[15]), "+f"(d[16]), "+f"(d[17]), "+f"(d[18]), "+f"(d[19])
               : "l"(descA), "l"(descB), "n"(scale_d), "n"(tnsp_a));
}
template <int scale_d> __device__ __forceinline__ void wgmma_n40_rs(float* d, const uint32_t* a, uint64_t descB) {
  asm volatile("{\n.reg .pred p;\nsetp.ne.b32 p, %25, 0;\n"
               "wgmma.mma_async.sync.aligned.m64n40k16.f32.bf16.bf16 {%0,%1,%2,%3,%4,%5,%6,%7,%8,%9,%10,%11,%12,%13,%14,%15,%16,%17,%18,%19}, {%20,%21,%22,%23}, %24, p, 1, 1, 1;\n}\n"
               : "+f"(d[0]), "+f"(d[1]), "+f"(d[2]), "+f"(d[3]), "+f"(d[4]), "+f"(d[5]), "+f"(d[6]), "+f"(d[7]), "+f"(d[8]), "+f"(d[9]), "+f"(d[10]), "+f"(d[11]), "+f"(d[12]), "+f"(d[13]), "+f"(d[14]), "+f"(d[15]), "+f"(d[16]), "+f"(d[17]), "+f"(d[18]), "+f"(d[19])
               : "r"(a[0]), "r"(a[1]), "r"(a[2]), "r"(a[3]), "l"(descB), "n"(scale_d));
}
__device__ __forceinline__ uint64_t make_desc(uint32_t addr, uint32_t lbo_bytes, uint32_t sbo_bytes) {
  return (uint64_t)((addr & 0x3FFFF) >> 4) | ((uint64_t)(lbo_bytes >> 4) << 16) | ((uint64_t)(sbo_bytes >> 4) << 32) | (1ull << 62);
}

__device__ __forceinline__ void ldsm_x4(uint32_t addr, uint32_t& r0, uint32_t& r1, uint32_t& r2, uint32_t& r3) {
  asm volatile("ldmatrix.sync.aligned.m8n8.x4.shared.b16 {%0,%1,%2,%3}, [%4];" : "=r"(r0), "=r"(r1), "=r"(r2), "=r"(r3) : "r"(addr) : "memory");
}
__device__ __forceinline__ void ldsm_x4_t(uint32_t addr, uint32_t& r0, uint32_t& r1, uint32_t& r2, uint32_t& r3) {
  asm volatile("ldmatrix.sync.aligned.m8n8.x4.trans.shared.b16 {%0,%1,%2,%3}, [%4];" : "=r"(r0), "=r"(r1), "=r"(r2), "=r"(r3) : "r"(addr) : "memory");
}
__device__ __forceinline__ void stsm_x4(uint32_t addr, uint32_t r0, uint32_t r1, uint32_t r2, uint32_t r3) {
  asm volatile("stmatrix.sync.aligned.m8n8.x4.shared.b16 [%0], {%1,%2,%3,%4};" :: "r"(addr), "r"(r0), "r"(r1), "r"(r2), "r"(r3) : "memory");
}
__device__ __forceinline__ void sts128(uint32_t addr, uint32_t a, uint32_t b, uint32_t c, uint32_t d) {
  asm volatile("st.shared.v4.u32 [%0], {%1,%2,%3,%4};" :: "r"(addr), "r"(a), "r"(b), "r"(c), "r"(d) : "memory");
}
__device__ __forceinline__ float lds32f(uint32_t addr) {
  float v;
  asm volatile("ld.shared.f32 %0, [%1];" : "=f"(v) : "r"(addr) : "memory");
  return v;
}
__device__ __forceinline__ void sts32f(uint32_t addr, float a) {
  asm volatile("st.shared.f32 [%0], %1;" :: "r"(addr), "f"(a) : "memory");
}
__device__ __forceinline__ void mma_bf16(float (&c)[4], uint32_t a0, uint32_t a1, uint32_t a2, uint32_t a3, uint32_t b0, uint32_t b1) {
  asm volatile("mma.sync.aligned.m16n8k16.row.col.f32.bf16.bf16.f32 {%0,%1,%2,%3}, {%4,%5,%6,%7}, {%8,%9}, {%0,%1,%2,%3};"
               : "+f"(c[0]), "+f"(c[1]), "+f"(c[2]), "+f"(c[3]) : "r"(a0), "r"(a1), "r"(a2), "r"(a3), "r"(b0), "r"(b1));
}
__device__ __forceinline__ void mma_bf16_z(float (&c)[4], uint32_t a0, uint32_t a1, uint32_t a2, uint32_t a3, uint32_t b0, uint32_t b1) {
  asm volatile("mma.sync.aligned.m16n8k16.row.col.f32.bf16.bf16.f32 {%0,%1,%2,%3}, {%4,%5,%6,%7}, {%8,%9}, {%10,%10,%10,%10};"
               : "=f"(c[0]), "=f"(c[1]), "=f"(c[2]), "=f"(c[3]) : "r"(a0), "r"(a1), "r"(a2), "r"(a3), "r"(b0), "r"(b1), "f"(0.f));
}
__device__ __forceinline__ uint32_t movm_t(uint32_t v) {
  uint32_t r;
  asm volatile("movmatrix.sync.aligned.m8n8.trans.b16 %0, %1;" : "=r"(r) : "r"(v));
  return r;
}
__device__ __forceinline__ uint32_t pack_bf16(float lo, float hi) {
  uint32_t r;
  asm("cvt.rn.bf16x2.f32 %0, %1, %2;" : "=r"(r) : "f"(hi), "f"(lo));
  return r;
}
__device__ __forceinline__ float bf_lo(uint32_t v) { return __uint_as_float(v << 16); }
__device__ __forceinline__ float bf_hi(uint32_t v) { return __uint_as_float(v & 0xFFFF0000u); }
__device__ __forceinline__ void split3(float x, uint32_t& h, uint32_t& m, uint32_t& l) {
  h = pack_bf16(x, 0.f); x -= bf_lo(h);
  m = pack_bf16(x, 0.f); x -= bf_lo(m);
  l = pack_bf16(x, 0.f);
}
__device__ __forceinline__ float ex2(float x) { float r; asm("ex2.approx.ftz.f32 %0, %1;" : "=f"(r) : "f"(x)); return r; }
__device__ __forceinline__ float rcp_fast(float x) { float r; asm("rcp.approx.ftz.f32 %0, %1;" : "=f"(r) : "f"(x)); return r; }
__device__ __forceinline__ void red_v4(float* p, float a, float b, float c, float d) {
  asm volatile("red.global.add.v4.f32 [%0], {%1, %2, %3, %4};" :: "l"(p), "f"(a), "f"(b), "f"(c), "f"(d) : "memory");
}
__device__ __forceinline__ uint4 ld_ll(const uint4* p) {
  uint4 v;
  asm volatile("{\n.reg .b64 a, b;\nld.relaxed.gpu.global.v2.b64 {a, b}, [%4];\nmov.b64 {%0, %1}, a;\nmov.b64 {%2, %3}, b;\n}\n"
               : "=r"(v.x), "=r"(v.y), "=r"(v.z), "=r"(v.w) : "l"(p) : "memory");
  return v;
}
__device__ __forceinline__ void st_b64(uint2* p, uint32_t a, uint32_t b) {
  asm volatile("{\n.reg .b64 v;\nmov.b64 v, {%1, %2};\nst.relaxed.gpu.global.b64 [%0], v;\n}\n" :: "l"(p), "r"(a), "r"(b) : "memory");
}
__device__ __forceinline__ void st_b128(uint4* p, uint32_t a, uint32_t b, uint32_t c, uint32_t d) {
  asm volatile("{\n.reg .b128 v;\nmov.b128 v, {%1, %2, %3, %4};\nst.relaxed.gpu.global.b128 [%0], v;\n}\n" :: "l"(p), "r"(a), "r"(b), "r"(c), "r"(d) : "memory");
}
__device__ __forceinline__ uint4 ld_b128(const uint4* p) {
  uint4 v;
  asm volatile("{\n.reg .b128 v;\nld.relaxed.gpu.global.b128 v, [%4];\nmov.b128 {%0, %1, %2, %3}, v;\n}\n" : "=r"(v.x), "=r"(v.y), "=r"(v.z), "=r"(v.w) : "l"(p) : "memory");
  return v;
}

constexpr float LOG2E = 1.4426950408889634f;

struct Params {
  const __nv_bfloat16* x0;
  const __nv_bfloat16* wA_qkv;
  const __nv_bfloat16* wA_o;
  const __nv_bfloat16* wB_qkv;
  const __nv_bfloat16* wB_phi;
  const __nv_bfloat16* wB_o;
  __nv_bfloat16* out;
};

#define ACC_DEF(d, n) _Pragma("unroll") for (int i_ = 0; i_ < (n); i_++) asm volatile("" : "=f"(d[i_]))
#define ACC_FENCE(d, n) _Pragma("unroll") for (int i_ = 0; i_ < (n); i_++) asm volatile("" : "+f"(d[i_]) :: "memory")
#define PIN(a, n) _Pragma("unroll") for (int i_ = 0; i_ < (n); i_++) asm volatile("" : "+f"((a)[i_]))
#define PINU(a, n) _Pragma("unroll") for (int i_ = 0; i_ < (n); i_++) asm volatile("" : "+r"((a)[i_]))

#define STAGE_V(acc, p0) { \
    _Pragma("unroll") for (int j_ = 0; j_ < 4; j_++) { \
      const float* a_ = (acc) + j_ * 8; \
      stsm_x4((p0) + (j_ >> 1) * 8192 + (srowoff >> 1) + ((((uint32_t)(j_ & 1) << 5) + lhi) ^ lsw2), \
              pack_bf16(rs0 * a_[0], rs0 * a_[1]), pack_bf16(rs1 * a_[2], rs1 * a_[3]), pack_bf16(rs0 * a_[4], rs0 * a_[5]), pack_bf16(rs1 * a_[6], rs1 * a_[7])); } }
#define FRAG(dst, acc, TR, grp) { \
    _Pragma("unroll") for (int i_ = 0; i_ < 16; i_++) { \
      const float r_ = (i_ & 1) ? rs1 : rs0; \
      const uint32_t w_ = pack_bf16(r_ * (acc)[2 * i_], r_ * (acc)[2 * i_ + 1]); \
      if (TR) (dst)[i_] = movm_t(w_); else (dst)[(i_ & 12) + (i_ & 1) * 2 + ((i_ >> 1) & 1)] = w_; } \
    if (warp == 7 && mm < 15) { \
      _Pragma("unroll") for (int j_ = 0; j_ < 4; j_++) \
        st_b128(g_halo + (size_t)(mm * 8 + jj) * 512 + ((grp) * 4 + j_) * 32 + lane, ((dst)[j_ * 4] & ~1u) | H_BIT(l), (dst)[j_ * 4 + 1], (dst)[j_ * 4 + 2], (dst)[j_ * 4 + 3]); } \
    PINU(dst, 16); }
#define FRAG_PUT(src, slot) if (warp < 7) { _Pragma("unroll") for (int j_ = 0; j_ < 4; j_++) \
      sts128(sbase + (slot) * SLOT + 2048 + warp * 2048 + j_ * 512 + lane * 16, (src)[j_ * 4], (src)[j_ * 4 + 1], (src)[j_ * 4 + 2], (src)[j_ * 4 + 3]); }
#define FRAG_GET(dst, slot) { _Pragma("unroll") for (int j_ = 0; j_ < 4; j_++) \
      asm volatile("ld.shared.v4.u32 {%0, %1, %2, %3}, [%4];" : "=r"((dst)[j_ * 4]), "=r"((dst)[j_ * 4 + 1]), "=r"((dst)[j_ * 4 + 2]), "=r"((dst)[j_ * 4 + 3]) \
                   : "r"(sbase + (slot) * SLOT + warp * 2048 + j_ * 512 + lane * 16) : "memory"); }
#define RW(j) (((j) >> 1) * 4 + ((j) & 1))
__device__ __forceinline__ float rmax16(const float* p) {
  float m[4];
#pragma unroll
  for (int j = 0; j < 4; j++) m[j] = fmaxf(fmaxf(p[RW(j)], p[RW(j + 4)]), fmaxf(p[RW(j + 8)], p[RW(j + 12)]));
  const float r = fmaxf(fmaxf(m[0], m[1]), fmaxf(m[2], m[3]));
  return fmaxf(r, __shfl_xor_sync(0xffffffffu, r, 1));
}
__device__ __forceinline__ float rmin16(const float* p) {
  float m[4];
#pragma unroll
  for (int j = 0; j < 4; j++) m[j] = fminf(fminf(p[RW(j)], p[RW(j + 4)]), fminf(p[RW(j + 8)], p[RW(j + 12)]));
  const float r = fminf(fminf(m[0], m[1]), fminf(m[2], m[3]));
  return fminf(r, __shfl_xor_sync(0xffffffffu, r, 1));
}
__device__ __forceinline__ float exps16(float* o, const float* p, float c, float b) {
  float s[4];
#pragma unroll
  for (int j = 0; j < 16; j++) { o[j] = ex2(fmaf(p[RW(j)], c, b)); if (j < 4) s[j] = o[j]; else s[j & 3] += o[j]; }
  return (s[0] + s[1]) + (s[2] + s[3]);
}
__device__ __forceinline__ void store16(const float* e, float sum, uint32_t dst, uint32_t dsw, int c0) {
  const float inv = rcp_fast(sum + __shfl_xor_sync(0xffffffffu, sum, 1));
#pragma unroll
  for (int j = 0; j < 2; j++)
    sts128(dst + (((c0 + j) << 4) ^ dsw), pack_bf16(e[j * 8] * inv, e[j * 8 + 1] * inv), pack_bf16(e[j * 8 + 2] * inv, e[j * 8 + 3] * inv),
           pack_bf16(e[j * 8 + 4] * inv, e[j * 8 + 5] * inv), pack_bf16(e[j * 8 + 6] * inv, e[j * 8 + 7] * inv));
}
__device__ __forceinline__ void expp16(uint32_t* o, const float* p, float c0, float b0, float c1, float b1) {
#pragma unroll
  for (int j = 0; j < 8; j++) {
    const float c = (j & 1) ? c1 : c0, b = (j & 1) ? b1 : b0;
    o[j] = pack_bf16(ex2(fmaf(p[2 * j], c, b)), ex2(fmaf(p[2 * j + 1], c, b)));
  }
}
__device__ __forceinline__ void extrema(float* m, const float* p, float c0, float c1) {
#pragma unroll
  for (int i = 0; i < 4; i++) {
    const float* q = p + (i >> 1) * 16 + (i & 1) * 2;
    m[(i >> 1) * 4 + (i & 1)] = fminf(fminf(fminf(q[0], q[1]), fminf(q[4], q[5])), fminf(fminf(q[8], q[9]), fminf(q[12], q[13])));
    m[(i >> 1) * 4 + (i & 1) + 2] = fmaxf(fmaxf(fmaxf(q[0], q[1]), fmaxf(q[4], q[5])), fmaxf(fmaxf(q[8], q[9]), fmaxf(q[12], q[13])));
  }
#pragma unroll
  for (int o = 1; o <= 2; o <<= 1)
#pragma unroll
    for (int i = 0; i < 8; i++) { const float x = __shfl_xor_sync(0xffffffffu, m[i], o); m[i] = (i & 2) ? fmaxf(m[i], x) : fminf(m[i], x); }
#pragma unroll
  for (int i = 0; i < 8; i++) m[i] *= ((i & 2) ? -1.f : 1.f) * ((i & 1) ? c1 : c0);
}
#define SCHED_FENCE() asm volatile("pmevent 0;" ::: "memory")

__global__ void __cluster_dims__(2, 1, 1) __launch_bounds__(384, 1)
mega_kernel(const __grid_constant__ CUtensorMap tm_x0, const __grid_constant__ CUtensorMap tm_xo, const __grid_constant__ CUtensorMap tm_os,
            const __grid_constant__ CUtensorMap tm_o, const __grid_constant__ CUtensorMap tm_wf,
            const __grid_constant__ CUtensorMap tm_wqA, const __grid_constant__ CUtensorMap tm_wqB,
            const __grid_constant__ CUtensorMap tm_woA, const __grid_constant__ CUtensorMap tm_woB,
            const __grid_constant__ CUtensorMap tm_phi, const Params prm) {
  extern __shared__ __align__(1024) uint8_t smem_raw[];
  const uint32_t sbase = smem_u32(smem_raw);
  const uint32_t bar_full = sbase + OFF_BAR;
  const uint32_t bar_done = bar_full + 384;
  const uint32_t bar_stat = bar_full + 768, bar_stat2 = bar_full + 776, bar_epi = bar_full + 784, bar_phi = bar_full + 936  , bar_halo = bar_full + 904  ;
  const uint32_t bar_xr = bar_full + 800, bar_lx = bar_full + 808, bar_kvf = bar_full + 816  , bar_stg = bar_full + 832;
  const uint32_t bar_chk = bar_full + 848;

  const int warp = __shfl_sync(0xffffffffu, threadIdx.x >> 5, 0), lane = threadIdx.x & 31;
  uint32_t rank;
  asm volatile("mov.u32 %0, %%cluster_ctarank;" : "=r"(rank));
  const int aux = (int)blockIdx.x - NMAIN, tp = (int)(blockIdx.x >> 1) - 4;
  const int gp = tp < 0 ? 0 : (tp < 32 ? tp & 7 : 1 + (tp - 32) % 7), me = tp < 0 ? tp + 8 : (tp < 32 ? tp >> 3 : 4 + (tp - 32) / 7);
  const int jj = me, cc = gp;
  const int cta = aux >= 0 ? -1 : (cc * 8 + jj) * 2 + (int)rank;
  const int mm = cc * 2 + (int)rank;

#define LOAD_EPOCH() const unsigned epoch = ld_relaxed(&g_flags.epoch.v), ep1 = epoch + 1; (void)epoch
  int budget = 1 << 22;

  if (cta >= 0) {
    {
      const int tx = threadIdx.x;
      const __nv_bfloat16* pf = (tx < 128) ? prm.x0 + (size_t)(mm * 128 + tx) * D_MODEL + jj * 128
                                           : prm.wA_qkv + (size_t)(jj * 128 + (tx & 63)) * 3072 + ((tx - 128) >> 6) * 1024 + jj * 128 + rank * 64;
      if (tx < 320) asm volatile("prefetch.global.L2 [%0];" :: "l"(pf));
      else if (tx == 320) prefetch_tmap(&tm_x0);
      else if (tx == 352) prefetch_tmap(&tm_wqA);
      else if (tx == 383) asm volatile("prefetch.global.L2 [%0];" :: "l"(&g_flags.epoch.v));
    }
    if (elect_one()) {
#pragma unroll
      for (int i = 0; i < 4; i++) {
        const int u = warp * 4 + i;
        mbar_init(bar_full + u * 8, ((u >= 4 && u < 11) || (u > 32 && u != 40)) ? 2 : 1); mbar_init(bar_done + u * 8, 16);
      }
      mbar_init(bar_stat + warp * 16, 0x111111181182ull >> (4 * warp) & 15);
      mbar_init(bar_stat + warp * 16 + 8, 0x111111121811ull >> (4 * warp) & 15);
      mbar_init(bar_chk + 112 + (warp & 7) * 8, 1);
      asm volatile("fence.mbarrier_init.release.cluster;" ::: "memory");
    }
    __syncthreads();
    asm volatile("barrier.cluster.arrive.relaxed.aligned;" ::: "memory");
  }

  if (cta < 0) {
    LOAD_EPOCH();
    const uint32_t buf = sbase + warp * SLOT, bar = sbase + OFF_BAR + warp * 16;
    const uint32_t lsw = (lane & 7) << 4, lhi = (lane >> 4) << 4, lrow = (lane & 15) * 128;
    const bool el = elect_one();
    if (el) {
      mbar_init(bar, 1); mbar_init(bar + 8, 1);
      asm volatile("fence.mbarrier_init.release.cluster;" ::: "memory");
    }
#pragma unroll 1
    for (int rd = 0; rd < (NLAYERS > 1 ? 5 : 2); rd++) {
      if (rd >= 2 && warp >= 8) break;
      const int tk = rd < 2 ? aux * 12 + warp : aux * 8 + warp;
      const int half = tk & 1;
      const int blk = rd < 2 ? (tk >> 1) * 2 + rd : (4 - rd) * 16 + (tk >> 1);
      const CUtensorMap* tm = rd < 2 ? &tm_wqA : (rd == 2 ? &tm_wqB : &tm_wf);
      const int j0 = (blk & 15) >> 1;
#define AUX_LOAD(n) { const uint32_t d_ = buf + ((n) & 1) * 8192, b_ = bar + ((n) & 1) * 8; const int r_ = kslice(j0, 2 * (n) + half) * 64; \
        mbar_expect_tx(b_, 8192); tma_load_2d(d_, tm, b_, blk * 64, r_); tma_load_2d(d_ + 4096, tm, b_, blk * 64, r_ + 32); }
      if (el) {
        if (rd == 3) { wait_flag(&g_flags.wfready[j0].v, ep1 * 16); fence_proxy_async_global(); }
        AUX_LOAD(0); AUX_LOAD(1);
      }
      __syncwarp();
      float cs[8][4];
#pragma unroll
      for (int i = 0; i < 8; i++) cs[i][0] = cs[i][1] = cs[i][2] = cs[i][3] = 0.f;
#pragma unroll 1
      for (int n = 0; n < 8; n++) {
        const uint32_t tb = buf + (n & 1) * 8192 + lrow;
        mbar_wait(bar + (n & 1) * 8, (n >> 1) & 1);
#pragma unroll
        for (int i = 0; i < 16; i++) {
          uint32_t b0, b1, b2, b3;
          ldsm_x4_t(tb + (i >> 2) * 2048 + (((i & 3) * 32 + lhi) ^ lsw), b0, b1, b2, b3);
          mma_bf16(cs[2 * (i & 3)], 0x3F803F80u, 0x3F803F80u, 0x3F803F80u, 0x3F803F80u, b0, b1);
          mma_bf16(cs[2 * (i & 3) + 1], 0x3F803F80u, 0x3F803F80u, 0x3F803F80u, 0x3F803F80u, b2, b3);
        }
        __syncwarp();
        if (el && n < 6) AUX_LOAD(n + 2);
        __syncwarp();
      }
      if (lane < 4) {
#pragma unroll
        for (int i = 0; i < 8; i++) st_b64(&g_colsum[rd >= 2][blk * 32 + i * 4 + lane][half], __float_as_uint(cs[i][0]), (__float_as_uint(cs[i][1]) & ~3u) | (ep1 & 3));
      }
      __syncwarp();
    }
  } else if (warp >= 8) {
    asm volatile("setmaxnreg.dec.sync.aligned.u32 40;");
    if (warp == 8) {
      const bool el = elect_one();
      cluster_wait();
      if (el) {
#pragma unroll 1
        for (int l = 0; l < NLAYERS; l++) {
          const uint32_t par = l & 1;
          const CUtensorMap* tqk = par ? &tm_wf : &tm_wqA;
          const CUtensorMap* tv = par ? &tm_wqB : &tm_wqA;
          const CUtensorMap* two = par ? &tm_woB : &tm_woA;
          if (l == 1) { LOAD_EPOCH(); wait_flag(&g_flags.wfready[jj].v, ep1 * 16); fence_proxy_async_global(); }
#pragma unroll 1
          for (int u = 0; u < 32; u++) {
            if (u >= 4) mbar_wait_sl(bar_done + (u - 4) * 8, par);
            else if (l) mbar_wait_sl(bar_done + (43 + u + (u >> 1)) * 8, par ^ 1);
            else if (u == 1) __nanosleep(STAG1);
            else if (u == 2) mbar_wait_sl(bar_full, 0);
            const uint32_t fb = bar_full + u * 8;
            const bool res = u < 4 ? (l || u >= 2) : (u < 11 || (u >= 18 && u < 22));
            mbar_expect_tx(fb, res ? QST : QST + SLOT);
            const int row = kslice(jj, u < 4 ? u & 1 : (u < 18 ? u - 2 : (u < 22 ? u - 6 : u - 20))) * 64 + (int)rank * 32;
            const int ps = u < 4 ? u >> 1 : (u >= 18), col = jj * 128 + ps * 64;
            const int c0 = par ? jj * 128 + (ps ? 0 : 1024) : col;
            const uint32_t dst = sbase + (u & 3) * QST + rank * 4096;
            tma_load_2d_mc(dst, tqk, fb, c0, row);
            tma_load_2d_mc(dst + 8192, tqk, fb, c0 + (par ? 64 : 1024), row);
            tma_load_2d_mc(dst + 16384, tv, fb, col + 2048, row);
            if (l == PRL && u >= PRU && u < PRU + 4) PROFT(473 + u - PRU);
          }
#pragma unroll 1
          for (int s = 0; s < 16; s++) {
            if (s < 5) { if (s != 2 && s != 4) mbar_wait_sl(bar_done + (28 + s) * 8, par); }
            else if (s != 14) mbar_wait_sl(bar_done + (27 + s - (s == 15)) * 8, par);
            const uint32_t fb = bar_full + (32 + s) * 8;
            mbar_expect_tx(fb, SLOT);
            tma_load_2d_mc(sbase + rank * 8192 + (uint32_t)((WO_BSLOT >> (4 * s)) & 15) * SLOT, two, fb, jj * 128 + (int)rank * 64, wslice(jj, s) * 64);
            const int ts = s + par;
            if (s >= 5 && ts < 8) {
              mbar_expect_tx(bar_chk - 8 + ts * 8, SLOT);
              tma_load_2d(sbase + (uint32_t)((WO_ASLOT(par) >> (4 * ts)) & 15) * SLOT, &tm_o, bar_chk - 8 + ts * 8, wslice(jj, ts) * 64, mm * 128);
            }
          }
        }
      }
      __syncwarp();
    } else if (warp == 9) {
      const bool el = elect_one();
      if (el) {
        PROFT(472);
        tma_load_2d(sbase + OFF_S, &tm_x0, bar_full, jj * 128, mm * 128);
        __nanosleep(STAG1);
        tma_load_2d(sbase + OFF_S + SLOT, &tm_x0, bar_full + 8, jj * 128 + 64, mm * 128);
      }
      __syncwarp();
      LOAD_EPOCH();
#pragma unroll 1
      for (int lp = 0; lp < 4 * NLAYERS; lp++) {
        const int l = lp >> 2, ph = lp & 3;
        if (ph == 3) continue;
        const uint32_t par = l & 1;
        const __nv_bfloat16* pb = g_obuf + (ph >> 1) * 64 + (size_t)(mm * 128 + (ph ? 0 : S_LEN) + (lane & 7) * 16 + (jj & 1) * 8) * D_MODEL + (jj >> 1) * 16;
        const CUtensorMap* tm = lp ? &tm_o : &tm_x0;
        const int row = mm * 128 + ((ph || !l) ? 0 : S_LEN);
        const uint32_t bit = ph ? O_BIT(l) : X_BIT(l - 1);
        const uint32_t slots = ph ? (uint32_t)(WO_ASLOT(par) >> (ph * 32 - 28)) : 0x8769876u;
        const unsigned long long fr = ph == 0 ? XPACE : ph == 1 ? (par ? 0x353535351Full : 0x35351F1Eull) : (par ? 0x27262524232232ull : 0x27262524233232ull);
        uint32_t rdy = (lp == 0 || (lp & 7) == 1) ? 0xFF : 0;
        mbar_wait_sl(ph ? bar_done + ((uint32_t)fr & 63) * 8 : (l ? bar_done + 47 * 8 : bar_full), ph ? par : (l ? par ^ 1 : 0));
#pragma unroll 1
        for (int i = 0; i < (ph == 1 ? 4 + par : 7); i++) {
          if (!((rdy >> i) & 1) && (i < NPOLL || ph == 1)) {
            const unsigned* pp = reinterpret_cast<const unsigned*>(pb + srcb(jj, i + ((lane >> 3) & (POLLW - 1)), ph) * 128);
            if (i == 0) __nanosleep(POLL0);
            unsigned v0 = ld_relaxed(pp);
            __nanosleep(POLLGAP);
            unsigned v1 = ld_relaxed(pp);
            uint32_t no;
#pragma unroll 1
            for (int it = 0; it < (1 << 18); it++) {
              no = __ballot_sync(0xffffffffu, (v0 ^ bit) & 1);
              if (!(no & 0xFF)) break;
              v0 = ld_relaxed(pp);
              no = __ballot_sync(0xffffffffu, (v1 ^ bit) & 1);
              if (!(no & 0xFF)) break;
              v1 = ld_relaxed(pp);
            }
            rdy = ((1 | (no & 0xFF00 ? 0 : 2) | (no & 0xFF0000 ? 0 : 4) | (no >> 24 ? 0 : 8)) & ((1 << POLLW) - 1)) << i;
          }
          if (ph || i >= XP0) mbar_wait_sl(bar_done + ((uint32_t)(fr >> (8 * i)) & 63) * 8, par);
          if (el) {
            if (i == 0) PROFT(320 + l * 16 + ph);
            const uint32_t cb = bar_chk + (ph >> 1) * 112 + i * 8;
            mbar_expect_tx(cb, SLOT);
            tma_load_2d(sbase + ((slots >> (4 * i)) & 15) * SLOT, tm, cb, srcb(jj, i, ph) * 128 + (ph >> 1) * 64, row);
          }
          __syncwarp();
        }
        if (ph == 0 && el) {
          if (l) { wait_flag(&g_flags.xready[l][mm].v, ep1 * 8); fence_proxy_async_global(); }
#pragma unroll 1
          for (int u = 11; u < 34; u++) {
            if (u == 18) u = 22;
            mbar_wait_sl(bar_done + (u - 4) * 8, par);
            if (u == 32) mbar_expect_tx(bar_xr, 2 * SLOT);
            tma_load_2d(sbase + OFF_RA + (u & 3) * SLOT, tm, u < 32 ? bar_full + u * 8 : bar_xr, kslice(jj, u < 18 ? u - 2 : (u < 32 ? u - 20 : u - 32)) * 64, row);
          }
        }
        __syncwarp();
      }
      cluster_wait();
    } else {
      const int hw = warp - 10;
      LOAD_EPOCH();
      const bool el = elect_one();
      cluster_wait();
      if (hw == 0) {
        mbar_wait_sl(bar_full + 8, 0);
        if (lane < 7) prefetch_tmap(lane == 0 ? &tm_os : lane == 1 ? &tm_o : lane == 2 ? &tm_wf : lane == 3 ? &tm_wqB : lane == 4 ? &tm_woA : lane == 5 ? &tm_woB : &tm_phi);
#pragma unroll 1
        for (int i = 0; i < (NLAYERS > 1 ? 9 : 0); i++) {
          if (i == 0 || i == 5) mbar_wait_sl(bar_done + (i >> 1) * 12, 0);
          if (el) {
            if (i == 0) { mbar_expect_tx(bar_phi, 2 * SLOT + 8192); tma_load_2d(sbase + OFF_PHI, &tm_phi, bar_phi, 0, jj * 128); }
            else tma_load_2d(sbase + (i > 4 ? 10 : 12) * SLOT - 4096 + i * 4096, &tm_wqB, bar_phi, (i > 4 ? 896 : 0) + jj * 128 + ((i - 1) >> 1) * 64, mm * 64 + (~i & 1) * 32);
          }
          __syncwarp();
          __nanosleep(PFGAP);
        }
      } else {
#pragma unroll 1
        for (int b = 0; b < 2; b++) {
          float4* z = reinterpret_cast<float4*>(g_kv[b] + (jj * 4) * KVH + mm * (4 * KVH / 16)) + lane;
#pragma unroll
          for (int i = 0; i < 5; i++) z[i * 32] = make_float4(0.f, 0.f, 0.f, 0.f);
        }
#pragma unroll 1
        for (int i = 0; i < 16; i++) {
          const int b = i >> 2;
          const uint32_t v = (b == 0 ? O_BIT(0) : b == 1 ? X_BIT(0) : H_BIT(0)) + 1;
          uint4* p = b < 2 ? reinterpret_cast<uint4*>(g_obuf + (size_t)(b * S_LEN + mm * 128 + (i & 3) * 32 + (lane >> 3) * 8) * D_MODEL + jj * 128 + (b ? 0 : 64)) + (lane & 7)
                           : g_halo + (size_t)(mm * 8 + jj) * 512 + i * 32 + lane;
          *p = make_uint4(v, v, v, v);
        }
        fence_proxy_async_global();
      }
      __syncwarp();
      uint32_t chkp = 0;
#pragma unroll 1
      for (int lp = 0; lp < 4 * NLAYERS; lp++) {
        const int l = lp >> 2, ph = (lp & 3) == 2 ? 2 - hw : (lp & 3);
        const uint32_t par = l & 1;
        int lane; asm volatile("mov.u32 %0, %%laneid;" : "=r"(lane));
        if ((lp & 3) == 2 || (hw && ph == 0)) {
          const uint32_t bit = ph ? O_BIT(l) : X_BIT(l - 1);
          uint32_t slots = ph ? (uint32_t)(WO_ASLOT(par) >> (ph * 32 - 28)) : 0x8769876u;
          const uint32_t a0 = sbase + (lane & 7) * 132 + (lane >> 3) * 32;
#pragma unroll 1
          for (int c = 0; c < 7; c++, slots >>= 4) {
            const uint32_t cb = bar_chk + 112 - hw * 112 + c * 8;
#pragma unroll 1
            for (int it = 0; it < (1 << 12); it++) {
              mbar_wait_sl(cb, (chkp >> c) & 1);
              chkp ^= 1u << c;
              if (el && c == 0) PROFT(ph == 1 ? 480 + l * 2 : 488 + l * 2 + (ph >> 1));
              if (lp == 0) break;
              uint32_t w[16];
#pragma unroll
              for (int i = 0; i < 16; i++) asm volatile("ld.shared.u32 %0, [%1];" : "=r"(w[i]) : "r"(a0 + (slots & 15) * SLOT + i * 1024) : "memory");
#pragma unroll
              for (int i = 0; i < 8; i++) w[i] = (w[i] ^ bit) | (w[i + 8] ^ bit);
              if (__all_sync(0xffffffffu, (((w[0] | w[1] | w[2]) | (w[3] | w[4] | w[5]) | (w[6] | w[7])) & 1) == 0)) break;
              if (el) {
                fence_proxy_async_smem();
                mbar_expect_tx(cb, SLOT);
                tma_load_2d(sbase + (slots & 15) * SLOT, &tm_o, cb, srcb(jj, c, ph) * 128 + (ph >> 1) * 64, mm * 128 + (ph ? 0 : S_LEN));
                RETRY_COUNT();
              }
              __syncwarp();
            }
            if (el) { mbar_arrive_local(bar_full + (c + (ph ? 25 + ph * 8 : 4)) * 8); if (lp == PRL * 4 && c == 0) PROFT(477); }
            __syncwarp();
          }
          if (ph) continue;
#pragma unroll 1
          for (int hp = 0; hp < 2; hp++) {
            const uint4* src = reinterpret_cast<const uint4*>(g_colsum[par][jj * 64 + hp * 32 + lane]);
            uint32_t bad;
            int it = 0;
            float c[6];
            do {
              bad = 0;
#pragma unroll
              for (int p = 0; p < 3; p++) {
                const uint4 v = ld_ll(src + ((par && p < 2) ? (hp ? -32 : 512) + p * 32 : p * 512));
                bad |= (v.y ^ ep1) | (v.w ^ ep1);
                c[2 * p] = __uint_as_float(v.x) + __uint_as_float(v.z); c[2 * p + 1] = __uint_as_float(v.y) + __uint_as_float(v.w);
              }
              bad &= 3;
              if (bad) __nanosleep(300);
            } while (bad && ++it < (1 << 16));
#pragma unroll
            for (int p = 0; p < 6; p++) {
              uint32_t h, m, lo;
              split3(c[p], h, m, lo);
              sts128(sbase + OFF_LNB + hp * 4096 + (p >> 1) * 1024 + lane * 32 + (p & 1) * 16, h | (m << 16), h | (lo << 16), h | (m << 16), lo | (m << 16));
            }
            fence_proxy_async_smem();
            __syncwarp();
            if (el) { mbar_arrive_local(hp ? bar_stat2 : bar_stat); if (hp == 0) PROFT(324 + l * 16); }
            __syncwarp();
          }
          continue;
        } else if (ph == 0) {
          mbar_wait_sl(bar_done + 24, par);
          const uint4* sp = reinterpret_cast<const uint4*>(g_stats + (size_t)(mm * 128) * 8) + lane;
#pragma unroll 1
          for (int hf = 0; hf < 4; hf++) {
            uint4 v[4];
            uint32_t bad;
            int it = 0;
            do {
              bad = 0;
#pragma unroll
              for (int i = 0; i < 4; i++) { v[i] = ld_ll(sp + (hf * 4 + i) * 32); bad |= (v[i].y ^ STAT_TAG(l)) | (v[i].w ^ STAT_TAG(l)); }
              bad &= 3;
              if (bad) __nanosleep(200);
            } while (bad && ++it < (1 << 16));
            __syncwarp();
            float mean = 0.f, m2 = 0.f;
#pragma unroll
            for (int i = 0; i < 4; i++) {
              float a = __uint_as_float(v[i].x) + __uint_as_float(v[i].z);
              a += __shfl_xor_sync(0xffffffffu, a, 1); a += __shfl_xor_sync(0xffffffffu, a, 2);
              a *= 0.125f;
              const float e0 = __uint_as_float(v[i].x) - a, e1 = __uint_as_float(v[i].z) - a;
              float q = fmaf(fmaf(e0, e0, e1 * e1), 128.f, __uint_as_float(v[i].y) + __uint_as_float(v[i].w));
              q += __shfl_xor_sync(0xffffffffu, q, 1); q += __shfl_xor_sync(0xffffffffu, q, 2);
              if ((lane & 3) == i) { mean = a; m2 = q; }
            }
            const uint32_t row = hf * 32 + (lane & 3) * 8 + (lane >> 2);
            uint32_t h, m, lo;
            split3(-0.5f * mean, h, m, lo);
            sts128(sbase + OFF_LNA + row * 16, h | (h << 16), m | (h << 16), lo | (m << 16), m | (lo << 16));
            sts32f(sbase + OFF_ST + row * 4, rsqrtf(m2 * (1.f / 1024.f) + 1e-5f));
          }
          fence_proxy_async_smem();
          __syncwarp();
          if (el) { mbar_arrive_local(bar_stat); PROFT(323 + l * 16); }
          __syncwarp();
#pragma unroll 1
          for (int i = 0; i < 8 - 4 * l; i++) {
            asm volatile("prefetch.global.L2 [%0];" :: "l"(i < 4 ? (l ? prm.wB_o : prm.wA_o) + (size_t)cta * 8192 + i * 2048 + lane * 64
                                                                 : prm.wB_qkv + (size_t)(cta * 8 + (i - 4) * 2 + (lane >> 4)) * 3072 + 2048 + (lane & 15) * 64));
            __nanosleep(PFGAP);
          }
          continue;
        }
        if (ph == 1 && par) {
          {
            if (hw == 0)
#pragma unroll 1
            for (int h = 0; h < 2; h++) {
              asm volatile("bar.sync %0, 288;" :: "r"(BAR_KV + h) : "memory");
              __syncwarp();
              PROFT(331 + l * 16 + h);
              if (lane < 16) signal_release(&g_flags.kvready[(l & 2) + h][jj][lane].v);
              const unsigned* kf = &g_flags.kvready[(l & 2) + h][jj][mm].v;
              unsigned v0 = ld_relaxed(kf);
              __nanosleep(150);
              unsigned v1 = ld_relaxed(kf);
#pragma unroll 1
              for (int it = 0; it < (1 << 18); it++) {
                if (v0 == ep1 * 16) break;
                v0 = ld_relaxed(kf);
                if (v1 == ep1 * 16) break;
                v1 = ld_relaxed(kf);
              }
              fence_acquire();
              __syncwarp();
              if (h) mbar_wait_sl(bar_lx, 1);
              if (el) {
                PROFT(333 + l * 16 + h);
                fence_proxy_async_global();
                mbar_expect_tx(bar_kvf + h * 8, 2 * KVH * 4);
#pragma unroll 1
                for (int i = 0; i < 4; i++)
                  asm volatile("cp.async.bulk.shared::cluster.global.mbarrier::complete_tx::bytes [%0], [%1], %2, [%3];"
                               :: "r"(sbase + ((i & 1) ? OFF_PHI + h * 4096 + (i >> 1) * 2048 : 11 * SLOT + (i >> 1) * 8192)),
                                  "l"(g_kv[l >> 1] + (jj * 4 + h * 2 + (i >> 1)) * KVH + (i & 1) * 2048), "r"((i & 1) ? 2048 : 8192), "r"(bar_kvf + h * 8) : "memory");
              }
              __syncwarp();
            }
          }
        } else if (ph == 1) {
#pragma unroll 1
          for (int i = 0; i < 2; i++) {
            if (i && lp + hw == 1 && NLAYERS > 1) {
#pragma unroll 1
              for (int c = 0; c < 8; c++) {
                if (!(c & 3)) asm volatile("bar.sync %0, 288;" :: "r"(BAR_WF + (c >> 2)) : "memory");
                if (el) {
                  tma_store_2d(&tm_wf, sbase + 11 * SLOT + c * 4096, (c < 4 ? 1024 : -128) + jj * 128 + (c >> 1) * 64, mm * 64 + (c & 1) * 32);
                  if ((c & 3) == 3) {
                    asm volatile("cp.async.bulk.commit_group;\ncp.async.bulk.wait_group.read 0;" ::: "memory");
                    mbar_arrive_local(bar_phi + (c >> 2) * 8);
                  } else __nanosleep(WFGAP);
                }
                __syncwarp();
              }
              if (el) { bulk_commit_wait(); signal_release(&g_flags.wfready[jj].v); PROFT(335); }
              __syncwarp();
            }
            mbar_wait_sl(bar_done + (i ? HW1 : (hw ? 19 : HW0)) * 8, 0);
            if (lp + hw == 2 && NLAYERS > 1) mbar_wait_sl(bar_phi, 1);
            const uint4* src = g_halo + (size_t)(mm * 8 + jj - 8) * 512 + i * 256 + hw * 128 + lane;
            uint4 v[4];
            int it = 0;
            bool ok;
            do {
#pragma unroll
              for (int j = 0; j < 4; j++) v[j] = mm ? ld_b128(src + j * 32) : make_uint4(H_BIT(l), 0, 0, 0);
              ok = __all_sync(0xffffffffu, (((v[0].x ^ H_BIT(l)) | (v[1].x ^ H_BIT(l)) | (v[2].x ^ H_BIT(l)) | (v[3].x ^ H_BIT(l))) & 1) == 0);
            } while (!ok && ++it < (1 << 16));
#pragma unroll
            for (int j = 0; j < 4; j++) sts128(sbase + OFF_S + hw * SLOT + j * 512 + lane * 16, v[j].x, v[j].y, v[j].z, v[j].w);
            __syncwarp();
            if (el) { mbar_arrive_local(bar_halo + hw * 8); PROFT(331 + l * 16 + i * 2 + hw); }
            __syncwarp();
          }
        } else if (hw == 0 && l < NLAYERS - 1) {
          bar_sync<BAR_X1, 288>();
          if (el) {
            PROFT(328 + l * 16);
            mbar_wait_sl(bar_full + XD * 8, par ^ 1);
            tma_store_2d(&tm_o, sbase + 11 * SLOT, jj * 128 + 64, mm * 128 + S_LEN);
            bulk_commit_wait();
            signal_release(&g_flags.xready[l + 1][mm].v);
            PROFT(330 + l * 16);
          }
          __syncwarp();
        }
      }
    }
    cluster_sync();
  } else {
    asm volatile("setmaxnreg.inc.sync.aligned.u32 232;");
    LOAD_EPOCH();
    const int wg = warp >> 2;
    const int r0 = warp * 16;
    const uint32_t pK = sbase + OFF_S, pV = sbase + OFF_S + SLOT;
#define PMASKS(on, bit) const uint32_t pm0 = ((on) && t == (g & 3) && (g >> 2) == (g & 1)), pm1 = ((on) && t == (g & 3) && (g >> 2) != (g & 1)), pbit = (bit)
#define PBIT0(w) (((w) & ~pm0) | (pbit & pm0))
#define PBIT1(w) (((w) & ~pm1) | (pbit & pm1))
#define LANE_CONSTS() \
    int lane; asm volatile("mov.u32 %0, %%laneid;" : "=r"(lane)); \
    const int g = lane >> 2, t = lane & 3; \
    const uint32_t srowoff = (r0 + (lane & 15)) * 128, lsw = (lane & 7) << 4, lhi = (lane >> 4) << 4, lsw2 = (lane & 6) << 3; \
    (void)g; (void)t; (void)srowoff; (void)lsw; (void)lhi; (void)lsw2;
    uint32_t stgp = 0, peer;
    asm volatile("mapa.shared::cluster.u32 %0, %1, %2;" : "=r"(peer) : "r"(sbase), "r"(rank ^ 1));
    peer -= sbase;
    const uint32_t dA0 = (((sbase & 0x3FFFF) + wg * 8192) >> 4) | 0x10000u, dB0 = ((sbase & 0x3FFFF) >> 4) | 0x2000000u;
    cluster_wait();
#define DESC(lo, hi) ((uint64_t)(uint32_t)(lo) | ((uint64_t)(hi) << 32))
#define STG_ARRIVE() { __syncwarp(); if (elect_one()) mbar_arrive_local(bar_stg); }
#define STG_WAIT() { mbar_wait(bar_stg, stgp); stgp ^= 1; }
#define PROFS() do {} while (0)
#define REL(addr) { if (elect_one()) { mbar_arrive_local(addr); asm volatile("mbarrier.arrive.shared::cluster.b64 _, [%0];" :: "r"((addr) + peer) : "memory"); } }
#define QSTEP(ACC, DA, SC, PRE) { \
      const uint32_t da = (DA), db = dB0 + (ub & 0x18) * (QST >> 7); \
      mbar_wait(ub, par); \
      PRE; \
      wgmma_fence(); \
      wgmma4_n192<SC>(ACC, da, db); \
      wgmma_commit(); PROFS(); }
#define QREL() { wgmma_wait<1>(); REL(ub + 376); ub += 8; }
#define RA_CUR (dA0 + (OFF_RA >> 4) + (ub & 0x18) * (SLOT >> 7))
#define PUMP1() { QSTEP(S1, RA_CUR, 1, {}); QREL(); }
#define PUMP0() { PUMP1(); SCHED_FENCE(); }
#define PUMP() if (h == 0) PUMP1()
#define WSTEP() { \
      const uint32_t s4 = (ub - bar_full - 256) >> 1; \
      const uint32_t da = dA0 + (((uint32_t)(WO_ASLOT(par) >> s4) & 15) << 10), db = dB0 + (((uint32_t)(WO_BSLOT >> s4) & 15) << 10); \
      mbar_wait(ub, par); \
      wgmma_fence(); \
      wgmma4_n128<1>(S1, da, db); \
      wgmma_commit(); PROFS(); \
      wgmma_wait<1>(); \
      if (s4) REL(ub + 376); \
      ub += 8; }
#define PUMPS(n) { _Pragma("unroll 1") for (int i_ = 0; i_ < (n); i_++) PUMP1(); }
#define SITE(n) { if ((BMASK >> (n)) & 1) PUMP1(); SCHED_FENCE(); }
#define LNSTEP(ACC, hh) { wgmma_fence(); wgmma_n192<1, 0>(ACC, make_desc(sbase + OFF_LNA + wg * 1024, 0, 128) ^ (1ull << 62), make_desc(sbase + OFF_LNB + (hh) * 4096, 0, 128) ^ (1ull << 62)); }
#define DRAIN_B(ACC) { \
      LANE_CONSTS(); \
      STAGE_V(ACC + 64, pV); \
      _Pragma("unroll") for (int i_ = 0; i_ < 64; i_++) st[i_] = ACC[i_]; \
      PIN(st, 64); }
#define WARP_STORE(tm, tile, col, row) { fence_proxy_async_smem(); __syncwarp(); \
      if (elect_one()) { tma_store_2d(tm, (tile) + r0 * 128, col, (row) + r0); asm volatile("cp.async.bulk.commit_group;" ::: "memory"); } __syncwarp(); }
#define PUBLISH_O() WARP_STORE(&tm_os, pO, jj * 128 + h * 64, mm * 128)
#define X_OUT(pc, on) { \
      PMASKS(on, X_BIT(l)); \
      _Pragma("unroll") for (int j = (pc) * 4; j < (pc) * 4 + 4; j++) \
        stsm_x4(pK + (pc) * SLOT + srowoff + ((((uint32_t)(j & 3) << 5) + lhi) ^ lsw), \
                PBIT0(pack_bf16(S1[j * 8 + 0], S1[j * 8 + 1])), PBIT0(pack_bf16(S1[j * 8 + 2], S1[j * 8 + 3])), \
                PBIT1(pack_bf16(S1[j * 8 + 4], S1[j * 8 + 5])), PBIT1(pack_bf16(S1[j * 8 + 6], S1[j * 8 + 7]))); }
#define REST_P1(SKEW) { \
      mbar_wait(bar_stat2, par); \
      LNSTEP(S1, 1); \
      _Pragma("unroll 1") while (ub < bar_full + 256) { \
        if (ub == bar_full + 256 - 8 * (SKEW) && wg == 0) bar_sync<BAR_SKEW, 256>(); \
        QSTEP(S1, RA_CUR, 1, {}); \
        if (ub == bar_full + 248 && wg == 1) bar_arrive<BAR_SKEW, 256>(); \
        QREL(); \
      } \
      mbar_wait(bar_done + (31 - (SKEW)) * 8, par);        \
      wgmma_wait<0>(); \
      ACC_FENCE(S1, 96); \
      REL(bar_done + 31 * 8); \
      PROF(13); }
#define FOLD(tile, rd) { \
          LANE_CONSTS(); \
          float d[32]; \
          ACC_DEF(d, 32); \
          mbar_wait(bar_phi, 0); \
          wgmma_fence(); \
          _Pragma("unroll") for (int i = 0; i < 2; i++) { \
            const uint64_t da = make_desc((tile) + wg * 8192 + i * 64, 16, 1024); \
            const uint64_t db = make_desc(sbase + OFF_PHI + wg * 4096 + i * 2048, 16, 512) ^ (3ull << 62); \
            wgmma_n32<0>(d + i * 16, da, db); wgmma_n32<1>(d + i * 16, da + 2, db + 64); \
          } \
          wgmma_commit(); \
          PUMP0(); \
          ACC_FENCE(d, 32); \
          bar_wg(wg); \
          _Pragma("unroll") for (int i = 0; i < 4; i++) { \
            const float* x = d + (i & 1) * 8 + (i >> 1) * 2; \
            if (rd) sts128((tile) + wg * 8192 + ((warp & 3) * 16 + (i >> 1) * 8 + g) * 128 + (((2 * t + (i & 1)) ^ g) << 4), \
                           pack_bf16(x[0], x[1]), pack_bf16(x[4], x[5]), pack_bf16(x[16], x[17]), pack_bf16(x[20], x[21])); \
            else stsm_x4((tile) + srowoff + ((((uint32_t)i << 5) + lhi) ^ lsw), pack_bf16(d[i * 8], d[i * 8 + 1]), pack_bf16(d[i * 8 + 2], d[i * 8 + 3]), \
                         pack_bf16(d[i * 8 + 4], d[i * 8 + 5]), pack_bf16(d[i * 8 + 6], d[i * 8 + 7])); \
          } \
          }
#define LOAD_X0(base) \
      _Pragma("unroll") for (int j = 0; j < 8; j++) { \
        uint32_t x0, x1, x2, x3; \
        ldsm_x4((base) + (j >> 2) * SLOT + srowoff + ((((uint32_t)(j & 3) << 5) + lhi) ^ lsw), x0, x1, x2, x3); \
        S1[j * 8 + 0] = bf_lo(x0); S1[j * 8 + 1] = bf_hi(x0); S1[j * 8 + 2] = bf_lo(x1); S1[j * 8 + 3] = bf_hi(x1); \
        S1[j * 8 + 4] = bf_lo(x2); S1[j * 8 + 5] = bf_hi(x2); S1[j * 8 + 6] = bf_lo(x3); S1[j * 8 + 7] = bf_hi(x3); \
      }
#define LOAD_X() { \
      wgmma_wait<0>(); \
      mbar_wait(bar_xr, par); \
      LOAD_X0(sbase + OFF_RA); \
      ACC_FENCE(S1, 64); \
      __syncwarp(); if (elect_one()) mbar_arrive_local(bar_lx); }

    float S1[96];
#pragma unroll
    for (int i = 0; i < 64; i++) S1[i] = 0.f;
#pragma unroll 1
    for (int l = 0; l < NLAYERS; l++) {
      const uint32_t par = l & 1;
      bar_wg(wg);
      PROF(0);
      uint32_t ub = bar_full;
      float S0[96];
      {
        LANE_CONSTS();
        ACC_DEF(S0, 96);
        QSTEP(S0, dA0 + (OFF_S >> 4), 0, {});
        ub += 8;
        PROF(1);
        if (l == 0) { mbar_wait(ub, 0); LOAD_X0(pK); }
        else { X_OUT(1, false); fence_proxy_async_smem(); }
        SCHED_FENCE();
        {
          float a0 = S1[0], a1 = S1[2], b0 = S1[1], b1 = S1[3];
#pragma unroll
          for (int i = 4; i < 64; i += 4) { a0 += S1[i]; b0 += S1[i + 1]; a1 += S1[i + 2]; b1 += S1[i + 3]; }
          a0 += b0; a1 += b1;
          a0 += __shfl_xor_sync(0xffffffffu, a0, 1); a1 += __shfl_xor_sync(0xffffffffu, a1, 1);
          a0 += __shfl_xor_sync(0xffffffffu, a0, 2); a1 += __shfl_xor_sync(0xffffffffu, a1, 2);
          a0 *= (1.f / 128.f); a1 *= (1.f / 128.f);
          asm volatile("" : "+f"(a0), "+f"(a1));
          bar_wg(wg);
          QSTEP(S0, dA0 + ((OFF_S + SLOT) >> 4), 1, wgmma_wait<0>());
          REL(ub + 376); ub += 8;
          SCHED_FENCE();
          float q0 = 0.f, q1 = 0.f;
          b0 = 0.f; b1 = 0.f;
#pragma unroll
          for (int i = 0; i < 64; i += 4) {
            const float d0 = S1[i] - a0, d1 = S1[i + 1] - a0, d2 = S1[i + 2] - a1, d3 = S1[i + 3] - a1;
            q0 = fmaf(d0, d0, q0); b0 = fmaf(d1, d1, b0); q1 = fmaf(d2, d2, q1); b1 = fmaf(d3, d3, b1);
          }
          q0 += b0; q1 += b1;
          q0 += __shfl_xor_sync(0xffffffffu, q0, 1); q1 += __shfl_xor_sync(0xffffffffu, q1, 1);
          q0 += __shfl_xor_sync(0xffffffffu, q0, 2); q1 += __shfl_xor_sync(0xffffffffu, q1, 2);
          if (t < 2) st_b64(g_stats + (size_t)(mm * 128 + r0 + g + t * 8) * 8 + jj, __float_as_uint(t ? a1 : a0), (__float_as_uint(t ? q1 : q0) & ~3u) | STAT_TAG(l));
        }
        if (l) { asm volatile("cp.async.bulk.wait_group 0;" ::: "memory"); bar_arrive<BAR_X1, 288>(); }
        ACC_DEF(S1, 96);
        QSTEP(S1, dA0 + (OFF_S >> 4), 0, {});
        QREL();
        QSTEP(S1, dA0 + ((OFF_S + SLOT) >> 4), 1, {});
        QREL();
#pragma unroll 1
        for (int i = 0; i < 14; i++) {
          QSTEP(S0, RA_CUR, 1, {});
          if (i == 0) PROF(2);
          QREL();
        }
      }
      LANE_CONSTS();
      mbar_wait(bar_stat, par);
      LNSTEP(S0, 0);
      wgmma_commit();
      const float rs0 = lds32f(sbase + OFF_ST + (r0 + g) * 4), rs1 = lds32f(sbase + OFF_ST + (r0 + g + 8) * 4);
      PUMP0();
      ACC_FENCE(S0, 96);
      PROF(3);
      if (!par) {
        constexpr uint32_t par = 0;
        uint32_t qa[16];
        uint32_t kf[32], vf[32];
#define DRAIN_A(ACC, hp, PMP) { \
          LANE_CONSTS(); \
          FRAG(kf + 16, ACC + 32, 0, (hp) * 2); \
          PMP; \
          FRAG(vf + 16, ACC + 64, 1, (hp) * 2 + 1); \
          _Pragma("unroll") for (int i_ = 0; i_ < 16; i_++) qa[i_] = pack_bf16(ACC[2 * i_], ACC[2 * i_ + 1]); \
          PINU(qa, 16); }
        DRAIN_A(S0, 0, PUMP0());
        if (l == 0 && NLAYERS > 1) {
#pragma unroll 1
          for (int rd = 1; rd >= 0; rd--) {
            FOLD(sbase + (12 - rd) * SLOT, rd);
            fence_proxy_async_smem();
            asm volatile("bar.arrive %0, 288;" :: "r"(BAR_WF + 1 - rd) : "memory");
          }
        }
        PUMPS(FPUMP);
        if (l == 0 && NLAYERS > 1) mbar_wait(bar_phi, 1);
#pragma unroll 1
        for (int h = 0; h < 2; h++) {
          const uint32_t pO = sbase + (h ? 3 : 12) * SLOT;
          PROF(4 + h * 12);
          LANE_CONSTS();
          FRAG_PUT(kf + 16, 10); FRAG_PUT(vf + 16, 11);
          STG_ARRIVE();
          if (h) { LOAD_X(); if (AW0) WSTEP(); } else PUMPS(HPUMP2);
          STG_WAIT();
          if (warp == 0) mbar_wait(bar_halo, h);
          FRAG_GET(kf, 10);
          PROF(5 + h * 12);
          float s[2][4][4];
#pragma unroll
          for (int ks = 0; ks < 2; ks++)
#pragma unroll
            for (int i = 0; i < 8; i++) {
              const int hh = (i >> 1) & 1, jb = (i & 1) + (~i >> 1 & 2);
              const uint32_t* b = kf + (jb >> 1) * 16 + hh * 8 + ks * 4 + (jb & 1) * 2;
              if (ks) mma_bf16(s[hh][jb], qa[hh * 8 + 4], qa[hh * 8 + 5], qa[hh * 8 + 6], qa[hh * 8 + 7], b[0], b[1]);
              else mma_bf16_z(s[hh][jb], qa[hh * 8], qa[hh * 8 + 1], qa[hh * 8 + 2], qa[hh * 8 + 3], b[0], b[1]);
            }
          PUMP();
          PROF(6 + h * 12);
          const bool e = g & 1, hb = (2 * t + (g & 1)) <= g;
          float va[2][2], vb[2][2], mx[2][2];
#pragma unroll
          for (int hh = 0; hh < 2; hh++) {
            va[hh][0] = e ? s[hh][1][1] : s[hh][1][0];
            vb[hh][0] = hb ? (e ? s[hh][2][1] : s[hh][2][0]) : (e ? s[hh][0][1] : s[hh][0][0]);
            va[hh][1] = e ? s[hh][2][3] : s[hh][2][2];
            vb[hh][1] = hb ? (e ? s[hh][3][3] : s[hh][3][2]) : (e ? s[hh][1][3] : s[hh][1][2]);
          }
          if (warp == 0 && mm == 0) {
#pragma unroll
            for (int hh = 0; hh < 2; hh++) { va[hh][0] = -INFINITY; if (!hb) { vb[hh][0] = -INFINITY; vb[hh][1] = -INFINITY; } }
          }
#pragma unroll
          for (int i = 0; i < 4; i++) mx[i >> 1][i & 1] = fmaxf(va[i >> 1][i & 1], vb[i >> 1][i & 1]);
#pragma unroll
          for (int o = 1; o <= 2; o <<= 1)
#pragma unroll
            for (int i = 0; i < 4; i++) mx[i >> 1][i & 1] = fmaxf(mx[i >> 1][i & 1], __shfl_xor_sync(0xffffffffu, mx[i >> 1][i & 1], o));
          const float sc0 = rs0 * (0.17677669529663687f * LOG2E), sc1 = rs1 * (0.17677669529663687f * LOG2E);
#pragma unroll
          for (int i = 0; i < 4; i++) {
            const float sc = (i & 1) ? sc1 : sc0, m = mx[i >> 1][i & 1];
            va[i >> 1][i & 1] = ex2((va[i >> 1][i & 1] - m) * sc); vb[i >> 1][i & 1] = ex2((vb[i >> 1][i & 1] - m) * sc);
            mx[i >> 1][i & 1] = va[i >> 1][i & 1] + vb[i >> 1][i & 1];
          }
          if (h == 0 && ASITE) { PIN(&va[0][0], 4); PIN(&vb[0][0], 4); PIN(&mx[0][0], 4); PUMP1(); }
          if (warp == 0) mbar_wait(bar_halo + 8, h);
          FRAG_GET(vf, 11);
#pragma unroll
          for (int o = 1; o <= 2; o <<= 1)
#pragma unroll
            for (int i = 0; i < 4; i++) mx[i >> 1][i & 1] += __shfl_xor_sync(0xffffffffu, mx[i >> 1][i & 1], o);
          const uint32_t selA = e ? 0x1044 : 0x4410, selB = e ? 0x3244 : 0x4432, selL = hb ? 0x4444 : selB, selH = hb ? selB : 0x4444;
          float o[2][4][4];
          uint32_t pa[2][8];
#pragma unroll
          for (int hh = 0; hh < 2; hh++) {
            const float i0 = rcp_fast(mx[hh][0]), i1 = rcp_fast(mx[hh][1]);
            const uint32_t w0 = pack_bf16(va[hh][0] * i0, vb[hh][0] * i0), w1 = pack_bf16(va[hh][1] * i1, vb[hh][1] * i1);
            pa[hh][0] = __byte_perm(w0, 0, selL); pa[hh][2] = __byte_perm(w0, 0, selA); pa[hh][3] = __byte_perm(w1, 0, selL);
            pa[hh][4] = __byte_perm(w0, 0, selH); pa[hh][5] = __byte_perm(w1, 0, selA); pa[hh][7] = __byte_perm(w1, 0, selH);
            pa[hh][1] = pa[hh][0] & pa[hh][4]; pa[hh][6] = pa[hh][3] & pa[hh][7];
          }
          PROF(7 + h * 12);
#pragma unroll
          for (int i = 0; i < 8; i++) mma_bf16_z(o[i >> 2][i & 3], pa[i >> 2][4], pa[i >> 2][5], pa[i >> 2][6], pa[i >> 2][7], vf[16 + 2 * i], vf[17 + 2 * i]);
#pragma unroll
          for (int i = 0; i < 8; i++) mma_bf16(o[i >> 2][i & 3], pa[i >> 2][0], pa[i >> 2][1], pa[i >> 2][2], pa[i >> 2][3], vf[2 * i], vf[2 * i + 1]);
          if (h == 0) PUMP1() else mbar_wait(bar_done + 30 * 8, par);
          if (NLAYERS > 1) mbar_wait(bar_phi + 8, 0);
#pragma unroll
          for (int i = 0; i < 4; i++) {
            const int hh = i >> 1, dp = i & 1;
            PMASKS(true, O_BIT(l));
            stsm_x4(pO + srowoff + ((hh * 64 + dp * 32 + lhi) ^ lsw), PBIT0(pack_bf16(o[hh][dp * 2][0], o[hh][dp * 2][1])), PBIT0(pack_bf16(o[hh][dp * 2][2], o[hh][dp * 2][3])),
                    PBIT1(pack_bf16(o[hh][dp * 2 + 1][0], o[hh][dp * 2 + 1][1])), PBIT1(pack_bf16(o[hh][dp * 2 + 1][2], o[hh][dp * 2 + 1][3])));
          }
          PUBLISH_O();
          PROF(11 + h * 12);
          if (h) break;
          REST_P1(ASKEW);
          asm volatile("cp.async.bulk.wait_group.read 0;" ::: "memory");
          DRAIN_A(S1, 1, {});
        }
      } else {
        constexpr uint32_t par = 1;
        float st[64];
        DRAIN_B(S0);
        if (warp < 2) sts128(sbase + OFF_ONES + warp * 512 + lane * 16, 0x3F803F80u, 0x3F803F80u, 0x3F803F80u, 0x3F803F80u);
        const float c0 = rs0 * LOG2E, c1 = rs1 * LOG2E;
#define KV_MMA(vs) { \
          const uint32_t dp = dA0 + 12 * 1024 - wg * 2560, dv = dA0 + (vs) * 1024 + ((OFF_ONES - (vs) * SLOT - 16) << 12) - wg * (512 << 16); \
          STG_WAIT(); \
          wgmma_fence(); \
          _Pragma("unroll") for (int ks = 0; ks < 8; ks++) { \
            const uint64_t a = DESC(dp + ks * 128, 0x40000040), b = DESC(dv + ks * (64 - (64 << 16)), 0x80000020); \
            if (ks == 0) wgmma_n40<0, 1>(kv, a, b); else wgmma_n40<1, 1>(kv, a, b); } \
          wgmma_commit(); }
#define KV_RED(hp) { \
          float* kvg = g_kv[l >> 1] + (jj * 4 + (hp) * 2 + wg) * KVH + ((warp & 3) * 32 + lane) * 4; \
          _Pragma("unroll") for (int i = 0; i < 4; i++) red_v4(kvg + i * 512, kv[i * 4], kv[i * 4 + 1], kv[i * 4 + 2], kv[i * 4 + 3]); \
          if (t == 0) red_v4(kvg + 2048, kv[16], kv[17], kv[18], kv[19]); \
          bar_arrive<BAR_KV + (hp), 288>(); }
#define KV_TILE(hp) { \
          LANE_CONSTS(); \
          float4 v[5]; \
          mbar_wait(bar_kvf + (hp) * 8, l >> 1); \
          PROF(25 + (hp)); \
          _Pragma("unroll") for (int i = 0; i < 5; i++) \
            asm volatile("ld.shared.v4.f32 {%0, %1, %2, %3}, [%4];" : "=f"(v[i].x), "=f"(v[i].y), "=f"(v[i].z), "=f"(v[i].w) \
                         : "r"(i < 4 ? pV + wg * 8192 + i * 2048 + (warp & 3) * 512 + lane * 16 : sbase + OFF_PHI + (hp) * 4096 + warp * 512 + g * 64) : "memory"); \
          bar_wg(wg); \
          const uint32_t e = lane & 7, jt = ((lane >> 1) & 4) + (e >> 1); \
          const uint32_t row = ((((warp >> 1) ^ wg) & 1) << 5) + ((jt & 1) << 4) + ((warp & 1) << 3) + (jt & 6) + (e & 1); \
          const uint32_t kd = pV + wg * 8192 + row * 128, ksw = (row & 7) << 4; \
          _Pragma("unroll") for (int i = 0; i < 2; i++) { \
            const float4 a = v[i * 2], b = v[i * 2 + 1]; \
            stsm_x4(kd + ((i * 32 + lhi) ^ ksw), pack_bf16(a.x, a.y), pack_bf16(a.z, a.w), pack_bf16(b.x, b.y), pack_bf16(b.z, b.w)); \
          } \
          stsm_x4(kd + ((64u + lhi) ^ ksw), pack_bf16(v[4].x, 1.f), pack_bf16(v[4].z, 1.f), 0u, 0u); }
#pragma unroll 1
        for (int h = 0; h < 2; h++) {
          PROF(4 + h * 2);
          SITE(0);
          LANE_CONSTS();
          const uint32_t dsw = (uint32_t)(g ^ (2 * t)) << 4, dst = ((t & 2) ? pK : sbase + 12 * SLOT) + (r0 + g) * 128;
          float e[16], f[16];
          float mn0 = rmin16(st);
          asm volatile("" : "+f"(mn0)); SCHED_FENCE();
          float sa = exps16(e, st, -c0, mn0 * c0), mx0 = rmax16(st);
          asm volatile("" : "+f"(sa), "+f"(mx0)); PIN(e, 16); SITE(1);
          if (h) STG_WAIT();
          store16(e, sa, dst, dsw, 4);
          float sb = exps16(f, st, c0, -mx0 * c0), mn1 = rmin16(st + 2);
          asm volatile("" : "+f"(sb), "+f"(mn1)); PIN(f, 16); SITE(2);
          store16(f, sb, dst, dsw, 0);
          float sc = exps16(e, st + 2, -c1, mn1 * c1), mx1 = rmax16(st + 2);
          asm volatile("" : "+f"(sc), "+f"(mx1)); PIN(e, 16); SITE(3);
          store16(e, sc, dst + 1024, dsw, 4);
          float sd = exps16(f, st + 2, c1, -mx1 * c1);
          asm volatile("" : "+f"(sd)); PIN(f, 16); SITE(4);
          store16(f, sd, dst + 1024, dsw, 0);
          PROF(5 + h * 2);
          if (h) break;
          {
            float kv[20];
            ACC_DEF(kv, 20);
            fence_proxy_async_smem();
            STG_ARRIVE();
            KV_MMA(11);
            PUMP0();
            ACC_FENCE(kv, 20);
            KV_RED(0);
            STG_ARRIVE();
          }
#pragma unroll
          for (int i = 0; i < 32; i++) st[i] = st[32 + i];
        }
        float mq[8];
        {
          float kv[20];
          mbar_wait(bar_stat2, par);
          LNSTEP(S1, 1);
          ub = bar_full + 240;
          PUMP1();
          if (wg == 0) bar_sync<BAR_SKEW, 256>();
          QSTEP(S1, RA_CUR, 1, {});
          if (wg == 1) bar_arrive<BAR_SKEW, 256>();
          QREL();
          if (KT0) KV_TILE(0);
          mbar_wait(bar_done + 30 * 8, par);
          wgmma_wait<0>();
          ACC_FENCE(S1, 96);
          if (!(RLATE & 2)) REL(bar_done + 31 * 8);
          PROF(13);
          LANE_CONSTS();
          STAGE_V(S1 + 64, sbase + 3 * SLOT);
          fence_proxy_async_smem();
          STG_ARRIVE();
          if (RLATE & 2) REL(bar_done + 31 * 8);
#pragma unroll
          for (int i = 0; i < 32; i++) st[i] = S1[i];
          PIN(st, 32);
          PROF(16);
          ACC_DEF(kv, 20);
          KV_MMA(3);
          SCHED_FENCE();
          extrema(mq, st, c0, c1);
          PIN(mq, 8);
          SCHED_FENCE();
          wgmma_wait<0>();
          ACC_FENCE(kv, 20);
          KV_RED(1);
          PROF(17);
        }
#pragma unroll 1
        for (int h = 0; h < 2; h++) {
          const uint32_t pO = sbase + (h ? 3 : 8) * SLOT;
          LANE_CONSTS();
          uint32_t fq[32];
          expp16(fq, st, -c0, mq[0], -c1, mq[1]); expp16(fq + 8, st, c0, mq[2], c1, mq[3]); PINU(fq, 16);
          PROF(18 + h * 14);
          if (h) {
            asm volatile("cp.async.bulk.wait_group.read 0;" ::: "memory");
            uint32_t n;
#pragma unroll 1
            while (ub < bar_full + 8 * FILL) {
              int it = 0;
              do {
                asm volatile("{\n.reg .pred p, q;\nsetp.ne.u32 q, %4, 0;\nmbarrier.test_wait.parity.shared::cta.b64 p, [%1], %2;\nand.pred p, p, q;\n"
                             "barrier.red.popc.aligned.u32 %0, %3, 128, p;\n}\n"
                             : "=r"(n) : "r"((warp & 3) ? ub : bar_kvf + 8), "r"((warp & 3) ? par : l >> 1), "r"(2 + wg), "r"((warp & 3) | (uint32_t)(lane == 0)) : "memory");
                n = __shfl_sync(0xffffffffu, n, 0);
              } while (n == 0 && ++it < (1 << 20));
              if (n & 1) break;
              WSTEP();
            }
          }
          if (h || !KT0) {
            KV_TILE(h);
            fence_proxy_async_smem();
            STG_ARRIVE();
          }
          SCHED_FENCE();
          expp16(fq + 16, st + 16, -c0, mq[4], -c1, mq[5]); PINU(fq + 16, 8);
          if (h || !KT0) STG_WAIT();
          wgmma_wait<0>();
          ACC_FENCE(S1, 64);
          PROF(19 + h * 14);
          float o[4][20];
#define O_MMA(hh) { \
            const uint64_t db = make_desc(pV + (hh) * 8192, 16, 1024); \
            ACC_DEF(o[(hh) * 2], 20); ACC_DEF(o[(hh) * 2 + 1], 20); \
            wgmma_fence(); \
            wgmma_n40_rs<0>(o[(hh) * 2], fq + (hh) * 16, db + 256); wgmma_n40_rs<0>(o[(hh) * 2 + 1], fq + (hh) * 16 + 8, db); \
            wgmma_n40_rs<1>(o[(hh) * 2], fq + (hh) * 16 + 4, db + 384); wgmma_n40_rs<1>(o[(hh) * 2 + 1], fq + (hh) * 16 + 12, db + 128); \
            wgmma_commit(); }
          O_MMA(0);
          SCHED_FENCE();
          expp16(fq + 24, st + 16, c0, mq[6], c1, mq[7]); PINU(fq + 24, 8);
          SCHED_FENCE();
          PMASKS(true, O_BIT(l));
#pragma unroll
          for (int hh = 0; hh < 2; hh++) {
            if (hh && !OW) O_MMA(1);
            wgmma_wait<0>();
            ACC_FENCE(o[hh * 2], 20); ACC_FENCE(o[hh * 2 + 1], 20);
            if (!hh && OW) { O_MMA(1); SCHED_FENCE(); }
            const float* x = o[hh * 2];
            const float* y = o[hh * 2 + 1];
            const float rx0 = rcp_fast(x[17]), ry0 = rcp_fast(y[17]), rx1 = rcp_fast(x[19]), ry1 = rcp_fast(y[19]);
            const float i0 = rcp_fast(fmaf(x[16], rx0, y[16] * ry0) + 1e-6f), i1 = rcp_fast(fmaf(x[18], rx1, y[18] * ry1) + 1e-6f);
            const float ax0 = rx0 * i0, ay0 = ry0 * i0, ax1 = rx1 * i1, ay1 = ry1 * i1;
#pragma unroll
            for (int dp = 0; dp < 2; dp++)
              stsm_x4(pO + srowoff + ((hh * 64 + dp * 32 + lhi) ^ lsw),
                      PBIT0(pack_bf16(fmaf(x[dp * 8], ax0, y[dp * 8] * ay0), fmaf(x[dp * 8 + 1], ax0, y[dp * 8 + 1] * ay0))),
                      PBIT0(pack_bf16(fmaf(x[dp * 8 + 2], ax1, y[dp * 8 + 2] * ay1), fmaf(x[dp * 8 + 3], ax1, y[dp * 8 + 3] * ay1))),
                      PBIT1(pack_bf16(fmaf(x[dp * 8 + 4], ax0, y[dp * 8 + 4] * ay0), fmaf(x[dp * 8 + 5], ax0, y[dp * 8 + 5] * ay0))),
                      PBIT1(pack_bf16(fmaf(x[dp * 8 + 6], ax1, y[dp * 8 + 6] * ay1), fmaf(x[dp * 8 + 7], ax1, y[dp * 8 + 7] * ay1))));
          }
          PUBLISH_O();
          PROF(20 + h * 14);
          if (h) break;
#pragma unroll
          for (int i = 0; i < 32; i++) st[i] = S1[32 + i];
          PIN(st, 32);
          LOAD_X();
          bar_wg(wg);
          WSTEP();
          SCHED_FENCE();
          extrema(mq, st, c0, c1);
          PIN(mq, 8);
          PROF(31);
        }
      }
      __syncwarp();
      if (elect_one()) mbar_arrive_local(bar_epi);
      bar_wg(wg);
#pragma unroll 1
      while (ub < bar_full + 384) {
        WSTEP();
        if (ub == bar_full + 8 * 41) { asm volatile("cp.async.bulk.wait_group.read 0;" ::: "memory"); PROF(35); }
        if (ub == bar_full + 8 * 42) PROF(36);
      }
      wgmma_wait<0>();
      ACC_FENCE(S1, 64);
      if (!RLATE) REL(bar_done + 47 * 8);
      PROF(37);
      {
        LANE_CONSTS();
        X_OUT(0, l < NLAYERS - 1);
        WARP_STORE(l < NLAYERS - 1 ? &tm_os : &tm_xo, pK, jj * 128, mm * 128 + (l < NLAYERS - 1 ? S_LEN : 0));
        if (RLATE) REL(bar_done + 47 * 8);
        if (l == NLAYERS - 1) {
          X_OUT(1, false);
          WARP_STORE(&tm_xo, pV, jj * 128 + 64, mm * 128);
          asm volatile("cp.async.bulk.wait_group 0;" ::: "memory");
        }
      }
#pragma unroll
      for (int i = 32; i < 64; i++) { uint32_t c; asm volatile("mov.b32 %0, %1;" : "=r"(c) : "f"(S1[i])); S1[i] = __uint_as_float(c); }
      PROF(38);
    }
    const int tid = threadIdx.x;
    if (tid == 0) {
      unsigned old = atomicAdd(&g_flags.done.v, 1);
      if (old == ep1 * NMAIN - 1) {
        asm volatile("st.relaxed.gpu.global.u32 [%0], %1;" :: "l"(&g_flags.epoch.v), "r"(ep1) : "memory");
      }
    }
    __syncwarp();
    cluster_sync();
  }
}

typedef CUresult (*PFN_encode)(CUtensorMap*, CUtensorMapDataType, cuuint32_t, void*, const cuuint64_t*, const cuuint64_t*,
                               const cuuint32_t*, const cuuint32_t*, CUtensorMapInterleave, CUtensorMapSwizzle,
                               CUtensorMapL2promotion, CUtensorMapFloatOOBfill);

CUtensorMap make_map(PFN_encode enc, const void* ptr, uint64_t inner, uint64_t outer, uint32_t box_inner, uint32_t box_outer,
                     CUtensorMapSwizzle swz = CU_TENSOR_MAP_SWIZZLE_128B) {
  CUtensorMap m;
  cuuint64_t dims[2] = {inner, outer};
  cuuint64_t strides[1] = {inner * 2};
  cuuint32_t box[2] = {box_inner, box_outer};
  cuuint32_t es[2] = {1, 1};
  enc(&m, CU_TENSOR_MAP_DATA_TYPE_BFLOAT16, 2, const_cast<void*>(ptr), dims, strides, box, es, CU_TENSOR_MAP_INTERLEAVE_NONE,
      swz, CU_TENSOR_MAP_L2_PROMOTION_L2_256B, CU_TENSOR_MAP_FLOAT_OOB_FILL_NONE);
  return m;
}

}

extern "C" void kernel_launch(void* const* d_in, const int* in_sizes, int n_in, void* d_out, int out_size) {
  (void)in_sizes; (void)n_in; (void)out_size;
  static PFN_encode enc = nullptr;
  if (!enc) {
    void* fn = nullptr;
    cudaDriverEntryPointQueryResult qr;
    cudaGetDriverEntryPoint("cuTensorMapEncodeTiled", &fn, cudaEnableDefault, &qr);
    enc = (PFN_encode)fn;
    cudaFuncSetAttribute(mega_kernel, cudaFuncAttributeMaxDynamicSharedMemorySize, SMEM_BYTES);
  }
  Params prm;
  prm.x0 = (const __nv_bfloat16*)d_in[0];
  prm.wA_qkv = (const __nv_bfloat16*)d_in[1];
  prm.wA_o = (const __nv_bfloat16*)d_in[2];
  prm.wB_qkv = (const __nv_bfloat16*)d_in[4];
  prm.wB_phi = (const __nv_bfloat16*)d_in[5];
  prm.wB_o = (const __nv_bfloat16*)d_in[6];
  prm.out = (__nv_bfloat16*)d_out;
  void *obuf = nullptr, *wf = nullptr;
  cudaGetSymbolAddress(&obuf, g_obuf);
  cudaGetSymbolAddress(&wf, g_wfold);
  CUtensorMap tm_x0 = make_map(enc, d_in[0], D_MODEL, S_LEN, 64, 128);
  CUtensorMap tm_xo = make_map(enc, d_out, D_MODEL, S_LEN, 64, 16);
  CUtensorMap tm_os = make_map(enc, obuf, D_MODEL, 2 * S_LEN, 64, 16);
  CUtensorMap tm_o = make_map(enc, obuf, D_MODEL, 2 * S_LEN, 64, 128);
  CUtensorMap tm_wf = make_map(enc, wf, 2048, D_MODEL, 64, 32);
  CUtensorMap tm_wqA = make_map(enc, d_in[1], 3 * D_MODEL, D_MODEL, 64, 32);
  CUtensorMap tm_wqB = make_map(enc, prm.wB_qkv, 3 * D_MODEL, D_MODEL, 64, 32);
  CUtensorMap tm_woA = make_map(enc, prm.wA_o, D_MODEL, D_MODEL, 64, 64);
  CUtensorMap tm_woB = make_map(enc, prm.wB_o, D_MODEL, D_MODEL, 64, 64);
  CUtensorMap tm_phi = make_map(enc, prm.wB_phi, 32, 1024, 32, 128, CU_TENSOR_MAP_SWIZZLE_64B);
  mega_kernel<<<NMAIN + NAUX, 384, SMEM_BYTES>>>(tm_x0, tm_xo, tm_os, tm_o, tm_wf, tm_wqA, tm_wqB, tm_woA, tm_woB, tm_phi, prm);
}
```

```cpp
#include <cuda_runtime.h>
#include <cuda.h>
#include <cuda_bf16.h>
#include <stdint.h>

#define NLAYERS 4

#define STAG1 300
#define HPUMP1 2
#define HPUMP2 1
#define ASKEW 2
#define FPUMP 3
#define PFGAP 100
#define POLLW 4
#define POLL0 0
#define POLLGAP 120
#define OW 1
#define NPOLL 4
#define AW0 1
#define RLATE 3
#define FSTART 0
#define MAPV 1
#define ORD 15
#define HW1 29
#define XPACE 0x06050401000000ull
#define XP0 4
#define HW0 18
#define XD 4
#define WFGAP 50
#define KVL 0
#define BMASK 0x1F
#define ASITE 1
namespace {

constexpr int S_LEN = 2048, D_MODEL = 1024;
constexpr int NAUX = 4, NMAIN = 128;
constexpr int SLOT = 16384;
constexpr int QST = 24576;
constexpr int OFF_RA = 6 * SLOT, OFF_S = 10 * SLOT;
constexpr int OFF_HALO = 13 * SLOT, OFF_LNB = OFF_HALO  , OFF_ONES = OFF_HALO + 3072;
constexpr int OFF_ST = OFF_HALO + 7168  , OFF_PHI = OFF_HALO + 8192;
constexpr int OFF_BAR = 14 * SLOT;
constexpr int OFF_LNA = OFF_BAR + 1024;
constexpr int SMEM_BYTES = OFF_LNA + 2048;
#define WO_ASLOT(par) ((par) ? 0x9876CAB39876CA98ull : 0x98C76BA398C7698Cull)
constexpr unsigned long long WO_BSLOT = 0x5432105421054210ull;
__device__ __forceinline__ int srcb(int j, int i, int ph) { return ((ORD >> ph) & 1) ? (i + (i >= j)) & 7 : (j + i + 1) & 7; }
__device__ __forceinline__ int kslice(int j, int i) { return i < 2 ? 2 * j + i : (i < 9 ? 2 * srcb(j, i - 2, 0) : 2 * srcb(j, i - 9, 3) + 1); }
__device__ __forceinline__ int wslice(int j, int s) { return 2 * ((s & 7) ? srcb(j, (s & 7) - 1, 1 + (s >> 3)) : j) + (s >> 3); }
constexpr int KVH = 6 * 128 * 4;

struct __align__(128) Flag { unsigned v; unsigned pad[31]; };
struct Flags {
  Flag xready[4][16];
  Flag wfready[8];
  Flag done;
  Flag epoch;
};

__device__ Flags g_flags;
__device__ __nv_bfloat16 g_obuf[2 * S_LEN * D_MODEL];
#define O_BIT(l) ((epoch * NLAYERS + (l) + 1) & 1u)
#define X_BIT(l) ((epoch * (NLAYERS - 1) + (l) + 1) & 1u)
__device__ __nv_bfloat16 g_wfold[D_MODEL * 2048];
__device__ uint4 g_halo[16 * 8 * 512];
__device__ __align__(128) float g_kv[2][32 * KVH];
__device__ __align__(128) uint2 g_colsum[2][1536][2];
__device__ __align__(128) uint2 g_stats[S_LEN * 8];
#define H_BIT(l) (NLAYERS > 2 ? (uint32_t)((l) == 0) : (ep1 & 1))
#define STAT_TAG(l) ((ep1 * NLAYERS + (l) + 1) & 3u)

#define RETRY_COUNT()
#define PRL 0
#define PRU 0
#define PROFL 1
#define PROFW 0
#define PROFT(i) do {} while (0)
#define PROF(i) do {} while (0)

__device__ __forceinline__ uint32_t smem_u32(const void* p) { return (uint32_t)__cvta_generic_to_shared(p); }
__device__ __forceinline__ bool elect_one() {
  uint32_t p;
  asm volatile("{\n.reg .pred p;\nelect.sync _|p, 0xffffffff;\nselp.u32 %0, 1, 0, p;\n}\n" : "=r"(p));
  return p != 0;
}
__device__ __forceinline__ void mbar_init(uint32_t bar, uint32_t cnt) {
  asm volatile("mbarrier.init.shared::cta.b64 [%0], %1;" :: "r"(bar), "r"(cnt));
}
__device__ __forceinline__ void mbar_expect_tx(uint32_t bar, uint32_t bytes) {
  asm volatile("mbarrier.arrive.expect_tx.shared::cta.b64 _, [%0], %1;" :: "r"(bar), "r"(bytes) : "memory");
}
#define mbar_wait(bar, parity) \
  asm volatile("{\n.reg .pred p, q;\nW_%=:\nmbarrier.try_wait.parity.shared::cta.b64 p, [%1], %2;\nadd.s32 %0, %0, -1;\n" \
               "setp.gt.and.s32 q, %0, 0, !p;\n@q bra.uni W_%=;\n}\n" : "+r"(budget) : "r"((uint32_t)(bar)), "r"((uint32_t)(parity)) : "memory")
#define mbar_wait_sl(bar, parity) \
  asm volatile("{\n.reg .pred p, q;\nW_%=:\nmbarrier.try_wait.parity.shared::cta.b64 p, [%1], %2, 20000;\nadd.s32 %0, %0, -64;\n" \
               "setp.gt.and.s32 q, %0, 0, !p;\n@q bra.uni W_%=;\n}\n" : "+r"(budget) : "r"((uint32_t)(bar)), "r"((uint32_t)(parity)) : "memory")
__device__ __forceinline__ void mbar_arrive_local(uint32_t bar) {
  asm volatile("mbarrier.arrive.shared::cta.b64 _, [%0];" :: "r"(bar) : "memory");
}
__device__ __forceinline__ void tma_load_2d(uint32_t dst, const CUtensorMap* tm, uint32_t bar, int c0, int c1) {
  asm volatile("cp.async.bulk.tensor.2d.shared::cluster.global.mbarrier::complete_tx::bytes [%0], [%1, {%3, %4}], [%2];"
               :: "r"(dst), "l"(tm), "r"(bar), "r"(c0), "r"(c1) : "memory");
}
__device__ __forceinline__ void tma_load_2d_mc(uint32_t dst, const CUtensorMap* tm, uint32_t bar, int c0, int c1) {
  asm volatile("cp.async.bulk.tensor.2d.shared::cluster.global.mbarrier::complete_tx::bytes.multicast::cluster [%0], [%1, {%3, %4}], [%2], %5;"
               :: "r"(dst), "l"(tm), "r"(bar), "r"(c0), "r"(c1), "h"((uint16_t)3) : "memory");
}
__device__ __forceinline__ void tma_store_2d(const CUtensorMap* tm, uint32_t src, int c0, int c1) {
  asm volatile("cp.async.bulk.tensor.2d.global.shared::cta.bulk_group [%0, {%2, %3}], [%1];"
               :: "l"(tm), "r"(src), "r"(c0), "r"(c1) : "memory");
}
__device__ __forceinline__ void bulk_commit_wait() {
  asm volatile("cp.async.bulk.commit_group;\ncp.async.bulk.wait_group 0;" ::: "memory");
}
__device__ __forceinline__ void prefetch_tmap(const CUtensorMap* tm) {
  asm volatile("prefetch.tensormap [%0];" :: "l"(tm) : "memory");
}
__device__ __forceinline__ void fence_proxy_async_global() { asm volatile("fence.proxy.async.global;" ::: "memory"); }
__device__ __forceinline__ void fence_proxy_async_smem() { asm volatile("fence.proxy.async.shared::cta;" ::: "memory"); }
__device__ __forceinline__ unsigned ld_relaxed(const unsigned* p) {
  unsigned v;
  asm volatile("ld.relaxed.gpu.global.u32 %0, [%1];" : "=r"(v) : "l"(p) : "memory");
  return v;
}
__device__ __forceinline__ void fence_acquire() { asm volatile("fence.acquire.gpu;" ::: "memory"); }
__device__ __forceinline__ void wait_flag(const unsigned* p, unsigned target) {
  int it = 0;
  while ((int)(ld_relaxed(p) - target) < 0 && ++it < (1 << 20)) {}
  fence_acquire();
}
__device__ __forceinline__ void signal_release(unsigned* p) {
  asm volatile("red.release.gpu.global.add.u32 [%0], 1;" :: "l"(p) : "memory");
}
template <int ID, int N> __device__ __forceinline__ void bar_arrive() { asm volatile("bar.arrive %0, %1;" :: "n"(ID), "n"(N) : "memory"); }
template <int ID, int N> __device__ __forceinline__ void bar_sync() { asm volatile("bar.sync %0, %1;" :: "n"(ID), "n"(N) : "memory"); }
__device__ __forceinline__ void bar_wg(int wg) { asm volatile("bar.sync %0, 128;" :: "r"(2 + wg) : "memory"); }
__device__ __forceinline__ void cluster_sync() {
  asm volatile("barrier.cluster.arrive.relaxed.aligned;\nbarrier.cluster.wait.aligned;" ::: "memory");
}
__device__ __forceinline__ void cluster_wait() { asm volatile("barrier.cluster.wait.acquire.aligned;" ::: "memory"); }
enum { BAR_X1 = 7, BAR_WF = 8  , BAR_SKEW = 10 };

__device__ __forceinline__ void wgmma_fence() { asm volatile("wgmma.fence.sync.aligned;" ::: "memory"); }
__device__ __forceinline__ void wgmma_commit() { asm volatile("wgmma.commit_group.sync.aligned;" ::: "memory"); }
template <int N> __device__ __forceinline__ void wgmma_wait() { asm volatile("wgmma.wait_group.sync.aligned %0;" :: "n"(N) : "memory"); }

template <int scale_d, int tnsp_b = 1> __device__ __forceinline__ void wgmma_n192(float* d, uint64_t descA, uint64_t descB) {
  asm volatile("{\n.reg .pred p;\nsetp.ne.b32 p, %98, 0;\n"
               "wgmma.mma_async.sync.aligned.m64n192k16.f32.bf16.bf16 {%0,%1,%2,%3,%4,%5,%6,%7,%8,%9,%10,%11,%12,%13,%14,%15,%16,%17,%18,%19,%20,%21,%22,%23,%24,%25,%26,%27,%28,%29,%30,%31,%32,%33,%34,%35,%36,%37,%38,%39,%40,%41,%42,%43,%44,%45,%46,%47,%48,%49,%50,%51,%52,%53,%54,%55,%56,%57,%58,%59,%60,%61,%62,%63,%64,%65,%66,%67,%68,%69,%70,%71,%72,%73,%74,%75,%76,%77,%78,%79,%80,%81,%82,%83,%84,%85,%86,%87,%88,%89,%90,%91,%92,%93,%94,%95}, %96, %97, p, 1, 1, 0, %99;\n}\n"
               : "+f"(d[0]), "+f"(d[1]), "+f"(d[2]), "+f"(d[3]), "+f"(d[4]), "+f"(d[5]), "+f"(d[6]), "+f"(d[7]), "+f"(d[8]), "+f"(d[9]), "+f"(d[10]), "+f"(d[11]), "+f"(d[12]), "+f"(d[13]), "+f"(d[14]), "+f"(d[15]), "+f"(d[16]), "+f"(d[17]), "+f"(d[18]), "+f"(d[19]), "+f"(d[20]), "+f"(d[21]), "+f"(d[22]), "+f"(d[23]), "+f"(d[24]), "+f"(d[25]), "+f"(d[26]), "+f"(d[27]), "+f"(d[28]), "+f"(d[29]), "+f"(d[30]), "+f"(d[31]), "+f"(d[32]), "+f"(d[33]), "+f"(d[34]), "+f"(d[35]), "+f"(d[36]), "+f"(d[37]), "+f"(d[38]), "+f"(d[39]), "+f"(d[40]), "+f"(d[41]), "+f"(d[42]), "+f"(d[43]), "+f"(d[44]), "+f"(d[45]), "+f"(d[46]), "+f"(d[47]), "+f"(d[48]), "+f"(d[49]), "+f"(d[50]), "+f"(d[51]), "+f"(d[52]), "+f"(d[53]), "+f"(d[54]), "+f"(d[55]), "+f"(d[56]), "+f"(d[57]), "+f"(d[58]), "+f"(d[59]), "+f"(d[60]), "+f"(d[61]), "+f"(d[62]), "+f"(d[63]), "+f"(d[64]), "+f"(d[65]), "+f"(d[66]), "+f"(d[67]), "+f"(d[68]), "+f"(d[69]), "+f"(d[70]), "+f"(d[71]), "+f"(d[72]), "+f"(d[73]), "+f"(d[74]), "+f"(d[75]), "+f"(d[76]), "+f"(d[77]), "+f"(d[78]), "+f"(d[79]), "+f"(d[80]), "+f"(d[81]), "+f"(d[82]), "+f"(d[83]), "+f"(d[84]), "+f"(d[85]), "+f"(d[86]), "+f"(d[87]), "+f"(d[88]), "+f"(d[89]), "+f"(d[90]), "+f"(d[91]), "+f"(d[92]), "+f"(d[93]), "+f"(d[94]), "+f"(d[95])
               : "l"(descA), "l"(descB), "n"(scale_d), "n"(tnsp_b));
}
template <int scale_d> __device__ __forceinline__ void wgmma4_n192(float* d, uint32_t da, uint32_t db) {
#define R_ "{%0,%1,%2,%3,%4,%5,%6,%7,%8,%9,%10,%11,%12,%13,%14,%15,%16,%17,%18,%19,%20,%21,%22,%23,%24,%25,%26,%27,%28,%29,%30,%31,%32,%33,%34,%35,%36,%37,%38,%39,%40,%41,%42,%43,%44,%45,%46,%47,%48,%49,%50,%51,%52,%53,%54,%55,%56,%57,%58,%59,%60,%61,%62,%63,%64,%65,%66,%67,%68,%69,%70,%71,%72,%73,%74,%75,%76,%77,%78,%79,%80,%81,%82,%83,%84,%85,%86,%87,%88,%89,%90,%91,%92,%93,%94,%95}"
  asm volatile("{\n.reg .pred p, q;\n.reg .b64 a, b;\nsetp.ne.b32 p, %98, 0;\nsetp.eq.b32 q, 0, 0;\nmov.b64 a, {%96, 0x40000040};\nmov.b64 b, {%97, 0x40000040};\n"
               "wgmma.mma_async.sync.aligned.m64n192k16.f32.bf16.bf16 " R_ ", a, b, p, 1, 1, 0, 1;\nadd.s64 a, a, 2;\nadd.s64 b, b, 128;\n"
               "wgmma.mma_async.sync.aligned.m64n192k16.f32.bf16.bf16 " R_ ", a, b, q, 1, 1, 0, 1;\nadd.s64 a, a, 2;\nadd.s64 b, b, 128;\n"
               "wgmma.mma_async.sync.aligned.m64n192k16.f32.bf16.bf16 " R_ ", a, b, q, 1, 1, 0, 1;\nadd.s64 a, a, 2;\nadd.s64 b, b, 128;\n"
               "wgmma.mma_async.sync.aligned.m64n192k16.f32.bf16.bf16 " R_ ", a, b, q, 1, 1, 0, 1;\n}\n"
               : "+f"(d[0]), "+f"(d[1]), "+f"(d[2]), "+f"(d[3]), "+f"(d[4]), "+f"(d[5]), "+f"(d[6]), "+f"(d[7]), "+f"(d[8]), "+f"(d[9]), "+f"(d[10]), "+f"(d[11]), "+f"(d[12]), "+f"(d[13]), "+f"(d[14]), "+f"(d[15]), "+f"(d[16]), "+f"(d[17]), "+f"(d[18]), "+f"(d[19]), "+f"(d[20]), "+f"(d[21]), "+f"(d[22]), "+f"(d[23]), "+f"(d[24]), "+f"(d[25]), "+f"(d[26]), "+f"(d[27]), "+f"(d[28]), "+f"(d[29]), "+f"(d[30]), "+f"(d[31]), "+f"(d[32]), "+f"(d[33]), "+f"(d[34]), "+f"(d[35]), "+f"(d[36]), "+f"(d[37]), "+f"(d[38]), "+f"(d[39]), "+f"(d[40]), "+f"(d[41]), "+f"(d[42]), "+f"(d[43]), "+f"(d[44]), "+f"(d[45]), "+f"(d[46]), "+f"(d[47]), "+f"(d[48]), "+f"(d[49]), "+f"(d[50]), "+f"(d[51]), "+f"(d[52]), "+f"(d[53]), "+f"(d[54]), "+f"(d[55]), "+f"(d[56]), "+f"(d[57]), "+f"(d[58]), "+f"(d[59]), "+f"(d[60]), "+f"(d[61]), "+f"(d[62]), "+f"(d[63]), "+f"(d[64]), "+f"(d[65]), "+f"(d[66]), "+f"(d[67]), "+f"(d[68]), "+f"(d[69]), "+f"(d[70]), "+f"(d[71]), "+f"(d[72]), "+f"(d[73]), "+f"(d[74]), "+f"(d[75]), "+f"(d[76]), "+f"(d[77]), "+f"(d[78]), "+f"(d[79]), "+f"(d[80]), "+f"(d[81]), "+f"(d[82]), "+f"(d[83]), "+f"(d[84]), "+f"(d[85]), "+f"(d[86]), "+f"(d[87]), "+f"(d[88]), "+f"(d[89]), "+f"(d[90]), "+f"(d[91]), "+f"(d[92]), "+f"(d[93]), "+f"(d[94]), "+f"(d[95])
               : "r"(da), "r"(db), "n"(scale_d));
#undef R_
}
template <int scale_d> __device__ __forceinline__ void wgmma4_n128(float* d, uint32_t da, uint32_t db) {
#define R_ "{%0,%1,%2,%3,%4,%5,%6,%7,%8,%9,%10,%11,%12,%13,%14,%15,%16,%17,%18,%19,%20,%21,%22,%23,%24,%25,%26,%27,%28,%29,%30,%31,%32,%33,%34,%35,%36,%37,%38,%39,%40,%41,%42,%43,%44,%45,%46,%47,%48,%49,%50,%51,%52,%53,%54,%55,%56,%57,%58,%59,%60,%61,%62,%63}"
  asm volatile("{\n.reg .pred p, q;\n.reg .b64 a, b;\nsetp.ne.b32 p, %66, 0;\nsetp.eq.b32 q, 0, 0;\nmov.b64 a, {%64, 0x40000040};\nmov.b64 b, {%65, 0x40000040};\n"
               "wgmma.mma_async.sync.aligned.m64n128k16.f32.bf16.bf16 " R_ ", a, b, p, 1, 1, 0, 1;\nadd.s64 a, a, 2;\nadd.s64 b, b, 128;\n"
               "wgmma.mma_async.sync.aligned.m64n128k16.f32.bf16.bf16 " R_ ", a, b, q, 1, 1, 0, 1;\nadd.s64 a, a, 2;\nadd.s64 b, b, 128;\n"
               "wgmma.mma_async.sync.aligned.m64n128k16.f32.bf16.bf16 " R_ ", a, b, q, 1, 1, 0, 1;\nadd.s64 a, a, 2;\nadd.s64 b, b, 128;\n"
               "wgmma.mma_async.sync.aligned.m64n128k16.f32.bf16.bf16 " R_ ", a, b, q, 1, 1, 0, 1;\n}\n"
               : "+f"(d[0]), "+f"(d[1]), "+f"(d[2]), "+f"(d[3]), "+f"(d[4]), "+f"(d[5]), "+f"(d[6]), "+f"(d[7]), "+f"(d[8]), "+f"(d[9]), "+f"(d[10]), "+f"(d[11]), "+f"(d[12]), "+f"(d[13]), "+f"(d[14]), "+f"(d[15]), "+f"(d[16]), "+f"(d[17]), "+f"(d[18]), "+f"(d[19]), "+f"(d[20]), "+f"(d[21]), "+f"(d[22]), "+f"(d[23]), "+f"(d[24]), "+f"(d[25]), "+f"(d[26]), "+f"(d[27]), "+f"(d[28]), "+f"(d[29]), "+f"(d[30]), "+f"(d[31]), "+f"(d[32]), "+f"(d[33]), "+f"(d[34]), "+f"(d[35]), "+f"(d[36]), "+f"(d[37]), "+f"(d[38]), "+f"(d[39]), "+f"(d[40]), "+f"(d[41]), "+f"(d[42]), "+f"(d[43]), "+f"(d[44]), "+f"(d[45]), "+f"(d[46]), "+f"(d[47]), "+f"(d[48]), "+f"(d[49]), "+f"(d[50]), "+f"(d[51]), "+f"(d[52]), "+f"(d[53]), "+f"(d[54]), "+f"(d[55]), "+f"(d[56]), "+f"(d[57]), "+f"(d[58]), "+f"(d[59]), "+f"(d[60]), "+f"(d[61]), "+f"(d[62]), "+f"(d[63])
               : "r"(da), "r"(db), "n"(scale_d));
#undef R_
}
template <int scale_d> __device__ __forceinline__ void wgmma_n32(float* d, uint64_t descA, uint64_t descB) {
  asm volatile("{\n.reg .pred p;\nsetp.ne.b32 p, %18, 0;\n"
               "wgmma.mma_async.sync.aligned.m64n32k16.f32.bf16.bf16 {%0,%1,%2,%3,%4,%5,%6,%7,%8,%9,%10,%11,%12,%13,%14,%15}, %16, %17, p, 1, 1, 0, 1;\n}\n"
               : "+f"(d[0]), "+f"(d[1]), "+f"(d[2]), "+f"(d[3]), "+f"(d[4]), "+f"(d[5]), "+f"(d[6]), "+f"(d[7]), "+f"(d[8]), "+f"(d[9]), "+f"(d[10]), "+f"(d[11]), "+f"(d[12]), "+f"(d[13]), "+f"(d[14]), "+f"(d[15])
               : "l"(descA), "l"(descB), "n"(scale_d));
}
template <int scale_d, int tnsp_a> __device__ __forceinline__ void wgmma_n40(float* d, uint64_t descA, uint64_t descB) {
  asm volatile("{\n.reg .pred p;\nsetp.ne.b32 p, %22, 0;\n"
               "wgmma.mma_async.sync.aligned.m64n40k16.f32.bf16.bf16 {%0,%1,%2,%3,%4,%5,%6,%7,%8,%9,%10,%11,%12,%13,%14,%15,%16,%17,%18,%19}, %20, %21, p, 1, 1, %23, 1;\n}\n"
               : "+f"(d[0]), "+f"(d[1]), "+f"(d[2]), "+f"(d[3]), "+f"(d[4]), "+f"(d[5]), "+f"(d[6]), "+f"(d[7]), "+f"(d[8]), "+f"(d[9]), "+f"(d[10]), "+f"(d[11]), "+f"(d[12]), "+f"(d[13]), "+f"(d[14]), "+f"(d[15]), "+f"(d[16]), "+f"(d[17]), "+f"(d[18]), "+f"(d[19])
               : "l"(descA), "l"(descB), "n"(scale_d), "n"(tnsp_a));
}
template <int scale_d> __device__ __forceinline__ void wgmma_n40_rs(float* d, const uint32_t* a, uint64_t descB) {
  asm volatile("{\n.reg .pred p;\nsetp.ne.b32 p, %25, 0;\n"
               "wgmma.mma_async.sync.aligned.m64n40k16.f32.bf16.bf16 {%0,%1,%2,%3,%4,%5,%6,%7,%8,%9,%10,%11,%12,%13,%14,%15,%16,%17,%18,%19}, {%20,%21,%22,%23}, %24, p, 1, 1, 1;\n}\n"
               : "+f"(d[0]), "+f"(d[1]), "+f"(d[2]), "+f"(d[3]), "+f"(d[4]), "+f"(d[5]), "+f"(d[6]), "+f"(d[7]), "+f"(d[8]), "+f"(d[9]), "+f"(d[10]), "+f"(d[11]), "+f"(d[12]), "+f"(d[13]), "+f"(d[14]), "+f"(d[15]), "+f"(d[16]), "+f"(d[17]), "+f"(d[18]), "+f"(d[19])
               : "r"(a[0]), "r"(a[1]), "r"(a[2]), "r"(a[3]), "l"(descB), "n"(scale_d));
}
__device__ __forceinline__ uint64_t make_desc(uint32_t addr, uint32_t lbo_bytes, uint32_t sbo_bytes) {
  return (uint64_t)((addr & 0x3FFFF) >> 4) | ((uint64_t)(lbo_bytes >> 4) << 16) | ((uint64_t)(sbo_bytes >> 4) << 32) | (1ull << 62);
}

__device__ __forceinline__ void ldsm_x4(uint32_t addr, uint32_t& r0, uint32_t& r1, uint32_t& r2, uint32_t& r3) {
  asm volatile("ldmatrix.sync.aligned.m8n8.x4.shared.b16 {%0,%1,%2,%3}, [%4];" : "=r"(r0), "=r"(r1), "=r"(r2), "=r"(r3) : "r"(addr) : "memory");
}
__device__ __forceinline__ void ldsm_x4_t(uint32_t addr, uint32_t& r0, uint32_t& r1, uint32_t& r2, uint32_t& r3) {
  asm volatile("ldmatrix.sync.aligned.m8n8.x4.trans.shared.b16 {%0,%1,%2,%3}, [%4];" : "=r"(r0), "=r"(r1), "=r"(r2), "=r"(r3) : "r"(addr) : "memory");
}
__device__ __forceinline__ void stsm_x4(uint32_t addr, uint32_t r0, uint32_t r1, uint32_t r2, uint32_t r3) {
  asm volatile("stmatrix.sync.aligned.m8n8.x4.shared.b16 [%0], {%1,%2,%3,%4};" :: "r"(addr), "r"(r0), "r"(r1), "r"(r2), "r"(r3) : "memory");
}
__device__ __forceinline__ void sts128(uint32_t addr, uint32_t a, uint32_t b, uint32_t c, uint32_t d) {
  asm volatile("st.shared.v4.u32 [%0], {%1,%2,%3,%4};" :: "r"(addr), "r"(a), "r"(b), "r"(c), "r"(d) : "memory");
}
__device__ __forceinline__ float lds32f(uint32_t addr) {
  float v;
  asm volatile("ld.shared.f32 %0, [%1];" : "=f"(v) : "r"(addr) : "memory");
  return v;
}
__device__ __forceinline__ void sts32f(uint32_t addr, float a) {
  asm volatile("st.shared.f32 [%0], %1;" :: "r"(addr), "f"(a) : "memory");
}
__device__ __forceinline__ void mma_bf16(float (&c)[4], uint32_t a0, uint32_t a1, uint32_t a2, uint32_t a3, uint32_t b0, uint32_t b1) {
  asm volatile("mma.sync.aligned.m16n8k16.row.col.f32.bf16.bf16.f32 {%0,%1,%2,%3}, {%4,%5,%6,%7}, {%8,%9}, {%0,%1,%2,%3};"
               : "+f"(c[0]), "+f"(c[1]), "+f"(c[2]), "+f"(c[3]) : "r"(a0), "r"(a1), "r"(a2), "r"(a3), "r"(b0), "r"(b1));
}
__device__ __forceinline__ void mma_bf16_z(float (&c)[4], uint32_t a0, uint32_t a1, uint32_t a2, uint32_t a3, uint32_t b0, uint32_t b1) {
  asm volatile("mma.sync.aligned.m16n8k16.row.col.f32.bf16.bf16.f32 {%0,%1,%2,%3}, {%4,%5,%6,%7}, {%8,%9}, {%10,%10,%10,%10};"
               : "=f"(c[0]), "=f"(c[1]), "=f"(c[2]), "=f"(c[3]) : "r"(a0), "r"(a1), "r"(a2), "r"(a3), "r"(b0), "r"(b1), "f"(0.f));
}
__device__ __forceinline__ uint32_t movm_t(uint32_t v) {
  uint32_t r;
  asm volatile("movmatrix.sync.aligned.m8n8.trans.b16 %0, %1;" : "=r"(r) : "r"(v));
  return r;
}
__device__ __forceinline__ uint32_t pack_bf16(float lo, float hi) {
  uint32_t r;
  asm("cvt.rn.bf16x2.f32 %0, %1, %2;" : "=r"(r) : "f"(hi), "f"(lo));
  return r;
}
__device__ __forceinline__ float bf_lo(uint32_t v) { return __uint_as_float(v << 16); }
__device__ __forceinline__ float bf_hi(uint32_t v) { return __uint_as_float(v & 0xFFFF0000u); }
__device__ __forceinline__ void split3(float x, uint32_t& h, uint32_t& m, uint32_t& l) {
  h = pack_bf16(x, 0.f); x -= bf_lo(h);
  m = pack_bf16(x, 0.f); x -= bf_lo(m);
  l = pack_bf16(x, 0.f);
}
__device__ __forceinline__ float ex2(float x) { float r; asm("ex2.approx.ftz.f32 %0, %1;" : "=f"(r) : "f"(x)); return r; }
__device__ __forceinline__ float rcp_fast(float x) { float r; asm("rcp.approx.ftz.f32 %0, %1;" : "=f"(r) : "f"(x)); return r; }
__device__ __forceinline__ void red_v4(float* p, float a, float b, float c, float d) {
  asm volatile("red.global.add.v4.f32 [%0], {%1, %2, %3, %4};" :: "l"(p), "f"(a), "f"(b), "f"(c), "f"(d) : "memory");
}
__device__ __forceinline__ uint4 ld_ll(const uint4* p) {
  uint4 v;
  asm volatile("{\n.reg .b64 a, b;\nld.relaxed.gpu.global.v2.b64 {a, b}, [%4];\nmov.b64 {%0, %1}, a;\nmov.b64 {%2, %3}, b;\n}\n"
               : "=r"(v.x), "=r"(v.y), "=r"(v.z), "=r"(v.w) : "l"(p) : "memory");
  return v;
}
__device__ __forceinline__ void st_b64(uint2* p, uint32_t a, uint32_t b) {
  asm volatile("{\n.reg .b64 v;\nmov.b64 v, {%1, %2};\nst.relaxed.gpu.global.b64 [%0], v;\n}\n" :: "l"(p), "r"(a), "r"(b) : "memory");
}
__device__ __forceinline__ void st_b128(uint4* p, uint32_t a, uint32_t b, uint32_t c, uint32_t d) {
  asm volatile("{\n.reg .b128 v;\nmov.b128 v, {%1, %2, %3, %4};\nst.relaxed.gpu.global.b128 [%0], v;\n}\n" :: "l"(p), "r"(a), "r"(b), "r"(c), "r"(d) : "memory");
}
__device__ __forceinline__ uint4 ld_b128(const uint4* p) {
  uint4 v;
  asm volatile("{\n.reg .b128 v;\nld.relaxed.gpu.global.b128 v, [%4];\nmov.b128 {%0, %1, %2, %3}, v;\n}\n" : "=r"(v.x), "=r"(v.y), "=r"(v.z), "=r"(v.w) : "l"(p) : "memory");
  return v;
}

constexpr float LOG2E = 1.4426950408889634f;

struct Params {
  const __nv_bfloat16* x0;
  const __nv_bfloat16* wA_qkv;
  const __nv_bfloat16* wA_o;
  const __nv_bfloat16* wB_qkv;
  const __nv_bfloat16* wB_phi;
  const __nv_bfloat16* wB_o;
  __nv_bfloat16* out;
};

#define ACC_DEF(d, n) _Pragma("unroll") for (int i_ = 0; i_ < (n); i_++) asm volatile("" : "=f"(d[i_]))
#define ACC_FENCE(d, n) _Pragma("unroll") for (int i_ = 0; i_ < (n); i_++) asm volatile("" : "+f"(d[i_]) :: "memory")
#define PIN(a, n) _Pragma("unroll") for (int i_ = 0; i_ < (n); i_++) asm volatile("" : "+f"((a)[i_]))
#define PINU(a, n) _Pragma("unroll") for (int i_ = 0; i_ < (n); i_++) asm volatile("" : "+r"((a)[i_]))

#define STAGE_V(acc, p0) { \
    _Pragma("unroll") for (int j_ = 0; j_ < 4; j_++) { \
      const float* a_ = (acc) + j_ * 8; \
      stsm_x4((p0) + (j_ >> 1) * 8192 + (srowoff >> 1) + ((((uint32_t)(j_ & 1) << 5) + lhi) ^ lsw2), \
              pack_bf16(rs0 * a_[0], rs0 * a_[1]), pack_bf16(rs1 * a_[2], rs1 * a_[3]), pack_bf16(rs0 * a_[4], rs0 * a_[5]), pack_bf16(rs1 * a_[6], rs1 * a_[7])); } }
#define FRAG(dst, acc, TR, grp) { \
    _Pragma("unroll") for (int i_ = 0; i_ < 16; i_++) { \
      const float r_ = (i_ & 1) ? rs1 : rs0; \
      const uint32_t w_ = pack_bf16(r_ * (acc)[2 * i_], r_ * (acc)[2 * i_ + 1]); \
      if (TR) (dst)[i_] = movm_t(w_); else (dst)[(i_ & 12) + (i_ & 1) * 2 + ((i_ >> 1) & 1)] = w_; } \
    if (warp == 7 && mm < 15) { \
      _Pragma("unroll") for (int j_ = 0; j_ < 4; j_++) \
        st_b128(g_halo + (size_t)(mm * 8 + jj) * 512 + ((grp) * 4 + j_) * 32 + lane, ((dst)[j_ * 4] & ~1u) | H_BIT(l), (dst)[j_ * 4 + 1], (dst)[j_ * 4 + 2], (dst)[j_ * 4 + 3]); } \
    PINU(dst, 16); }
#define FRAG_PUT(src, slot) if (warp < 7) { _Pragma("unroll") for (int j_ = 0; j_ < 4; j_++) \
      sts128(sbase + (slot) * SLOT + 2048 + warp * 2048 + j_ * 512 + lane * 16, (src)[j_ * 4], (src)[j_ * 4 + 1], (src)[j_ * 4 + 2], (src)[j_ * 4 + 3]); }
#define FRAG_GET(dst, slot) { _Pragma("unroll") for (int j_ = 0; j_ < 4; j_++) \
      asm volatile("ld.shared.v4.u32 {%0, %1, %2, %3}, [%4];" : "=r"((dst)[j_ * 4]), "=r"((dst)[j_ * 4 + 1]), "=r"((dst)[j_ * 4 + 2]), "=r"((dst)[j_ * 4 + 3]) \
                   : "r"(sbase + (slot) * SLOT + warp * 2048 + j_ * 512 + lane * 16) : "memory"); }
#define RW(j) (((j) >> 1) * 4 + ((j) & 1))
__device__ __forceinline__ float rmax16(const float* p) {
  float m[4];
#pragma unroll
  for (int j = 0; j < 4; j++) m[j] = fmaxf(fmaxf(p[RW(j)], p[RW(j + 4)]), fmaxf(p[RW(j + 8)], p[RW(j + 12)]));
  const float r = fmaxf(fmaxf(m[0], m[1]), fmaxf(m[2], m[3]));
  return fmaxf(r, __shfl_xor_sync(0xffffffffu, r, 1));
}
__device__ __forceinline__ float rmin16(const float* p) {
  float m[4];
#pragma unroll
  for (int j = 0; j < 4; j++) m[j] = fminf(fminf(p[RW(j)], p[RW(j + 4)]), fminf(p[RW(j + 8)], p[RW(j + 12)]));
  const float r = fminf(fminf(m[0], m[1]), fminf(m[2], m[3]));
  return fminf(r, __shfl_xor_sync(0xffffffffu, r, 1));
}
__device__ __forceinline__ float exps16(float* o, const float* p, float c, float b) {
  float s[4];
#pragma unroll
  for (int j = 0; j < 16; j++) { o[j] = ex2(fmaf(p[RW(j)], c, b)); if (j < 4) s[j] = o[j]; else s[j & 3] += o[j]; }
  return (s[0] + s[1]) + (s[2] + s[3]);
}
__device__ __forceinline__ void store16(const float* e, float sum, uint32_t dst, uint32_t dsw, int c0) {
  const float inv = rcp_fast(sum + __shfl_xor_sync(0xffffffffu, sum, 1));
#pragma unroll
  for (int j = 0; j < 2; j++)
    sts128(dst + (((c0 + j) << 4) ^ dsw), pack_bf16(e[j * 8] * inv, e[j * 8 + 1] * inv), pack_bf16(e[j * 8 + 2] * inv, e[j * 8 + 3] * inv),
           pack_bf16(e[j * 8 + 4] * inv, e[j * 8 + 5] * inv), pack_bf16(e[j * 8 + 6] * inv, e[j * 8 + 7] * inv));
}
__device__ __forceinline__ void expp16(uint32_t* o, const float* p, float c0, float b0, float c1, float b1) {
#pragma unroll
  for (int j = 0; j < 8; j++) {
    const float c = (j & 1) ? c1 : c0, b = (j & 1) ? b1 : b0;
    o[j] = pack_bf16(ex2(fmaf(p[2 * j], c, b)), ex2(fmaf(p[2 * j + 1], c, b)));
  }
}
__device__ __forceinline__ void extrema(float* m, const float* p, float c0, float c1) {
#pragma unroll
  for (int i = 0; i < 4; i++) {
    const float* q = p + (i >> 1) * 16 + (i & 1) * 2;
    m[(i >> 1) * 4 + (i & 1)] = fminf(fminf(fminf(q[0], q[1]), fminf(q[4], q[5])), fminf(fminf(q[8], q[9]), fminf(q[12], q[13])));
    m[(i >> 1) * 4 + (i & 1) + 2] = fmaxf(fmaxf(fmaxf(q[0], q[1]), fmaxf(q[4], q[5])), fmaxf(fmaxf(q[8], q[9]), fmaxf(q[12], q[13])));
  }
#pragma unroll
  for (int o = 1; o <= 2; o <<= 1)
#pragma unroll
    for (int i = 0; i < 8; i++) { const float x = __shfl_xor_sync(0xffffffffu, m[i], o); m[i] = (i & 2) ? fmaxf(m[i], x) : fminf(m[i], x); }
#pragma unroll
  for (int i = 0; i < 8; i++) m[i] *= ((i & 2) ? -1.f : 1.f) * ((i & 1) ? c1 : c0);
}
#define SCHED_FENCE() asm volatile("pmevent 0;" ::: "memory")

__global__ void __cluster_dims__(2, 1, 1) __launch_bounds__(384, 1)
mega_kernel(const __grid_constant__ CUtensorMap tm_x0, const __grid_constant__ CUtensorMap tm_xo, const __grid_constant__ CUtensorMap tm_os,
            const __grid_constant__ CUtensorMap tm_o, const __grid_constant__ CUtensorMap tm_wf,
            const __grid_constant__ CUtensorMap tm_wqA, const __grid_constant__ CUtensorMap tm_wqB,
            const __grid_constant__ CUtensorMap tm_woA, const __grid_constant__ CUtensorMap tm_woB,
            const __grid_constant__ CUtensorMap tm_phi, const Params prm) {
  extern __shared__ __align__(1024) uint8_t smem_raw[];
  const uint32_t sbase = smem_u32(smem_raw);
  const uint32_t bar_full = sbase + OFF_BAR;
  const uint32_t bar_done = bar_full + 384;
  const uint32_t bar_stat = bar_full + 768, bar_stat2 = bar_full + 776, bar_epi = bar_full + 784, bar_phi = bar_full + 936  , bar_halo = bar_full + 904  ;
  const uint32_t bar_xr = bar_full + 800, bar_lx = bar_full + 808, bar_stg = bar_full + 832;
  const uint32_t bar_chk = bar_full + 848;

  const int warp = __shfl_sync(0xffffffffu, threadIdx.x >> 5, 0), lane = threadIdx.x & 31;
  uint32_t rank;
  asm volatile("mov.u32 %0, %%cluster_ctarank;" : "=r"(rank));
  const int aux = (int)blockIdx.x - NMAIN, tp = (int)(blockIdx.x >> 1) - 4;
  const int gp = tp < 0 ? 0 : (tp < 32 ? tp & 7 : 1 + (tp - 32) % 7), me = tp < 0 ? tp + 8 : (tp < 32 ? tp >> 3 : 4 + (tp - 32) / 7);
  const int jj = me, cc = gp;
  const int cta = aux >= 0 ? -1 : (cc * 8 + jj) * 2 + (int)rank;
  const int mm = cc * 2 + (int)rank;

#define LOAD_EPOCH() const unsigned epoch = ld_relaxed(&g_flags.epoch.v), ep1 = epoch + 1; (void)epoch
  int budget = 1 << 22;

  if (cta >= 0) {
    {
      const int tx = threadIdx.x;
      const __nv_bfloat16* pf = (tx < 128) ? prm.x0 + (size_t)(mm * 128 + tx) * D_MODEL + jj * 128
                                           : prm.wA_qkv + (size_t)(jj * 128 + (tx & 63)) * 3072 + ((tx - 128) >> 6) * 1024 + jj * 128 + rank * 64;
      if (tx < 320) asm volatile("prefetch.global.L2 [%0];" :: "l"(pf));
      else if (tx == 320) prefetch_tmap(&tm_x0);
      else if (tx == 352) prefetch_tmap(&tm_wqA);
      else if (tx == 383) asm volatile("prefetch.global.L2 [%0];" :: "l"(&g_flags.epoch.v));
    }
    if (elect_one()) {
#pragma unroll
      for (int i = 0; i < 4; i++) {
        const int u = warp * 4 + i;
        mbar_init(bar_full + u * 8, ((u >= 4 && u < 11) || (u > 32 && u != 40)) ? 2 : 1); mbar_init(bar_done + u * 8, 16);
      }
      mbar_init(bar_stat + warp * 16, 0x111111181182ull >> (4 * warp) & 15);
      mbar_init(bar_stat + warp * 16 + 8, 0x111111121811ull >> (4 * warp) & 15);
      mbar_init(bar_chk + 112 + (warp & 7) * 8, 1);
      asm volatile("fence.mbarrier_init.release.cluster;" ::: "memory");
    }
    __syncthreads();
    asm volatile("barrier.cluster.arrive.relaxed.aligned;" ::: "memory");
  }

  if (cta < 0) {
    LOAD_EPOCH();
    const uint32_t buf = sbase + warp * SLOT, bar = sbase + OFF_BAR + warp * 16;
    const uint32_t lsw = (lane & 7) << 4, lhi = (lane >> 4) << 4, lrow = (lane & 15) * 128;
    const bool el = elect_one();
    if (el) {
      mbar_init(bar, 1); mbar_init(bar + 8, 1);
      asm volatile("fence.mbarrier_init.release.cluster;" ::: "memory");
    }
#pragma unroll 1
    for (int rd = 0; rd < (NLAYERS > 1 ? 5 : 2); rd++) {
      if (rd >= 2 && warp >= 8) break;
      const int tk = rd < 2 ? aux * 12 + warp : aux * 8 + warp;
      const int half = tk & 1;
      const int blk = rd < 2 ? (tk >> 1) * 2 + rd : (4 - rd) * 16 + (tk >> 1);
      const CUtensorMap* tm = rd < 2 ? &tm_wqA : (rd == 2 ? &tm_wqB : &tm_wf);
      const int j0 = (blk & 15) >> 1;
#define AUX_LOAD(n) { const uint32_t d_ = buf + ((n) & 1) * 8192, b_ = bar + ((n) & 1) * 8; const int r_ = kslice(j0, 2 * (n) + half) * 64; \
        mbar_expect_tx(b_, 8192); tma_load_2d(d_, tm, b_, blk * 64, r_); tma_load_2d(d_ + 4096, tm, b_, blk * 64, r_ + 32); }
      if (el) {
        if (rd == 3) { wait_flag(&g_flags.wfready[j0].v, ep1 * 16); fence_proxy_async_global(); }
        AUX_LOAD(0); AUX_LOAD(1);
      }
      __syncwarp();
      float cs[8][4];
#pragma unroll
      for (int i = 0; i < 8; i++) cs[i][0] = cs[i][1] = cs[i][2] = cs[i][3] = 0.f;
#pragma unroll 1
      for (int n = 0; n < 8; n++) {
        const uint32_t tb = buf + (n & 1) * 8192 + lrow;
        mbar_wait(bar + (n & 1) * 8, (n >> 1) & 1);
#pragma unroll
        for (int i = 0; i < 16; i++) {
          uint32_t b0, b1, b2, b3;
          ldsm_x4_t(tb + (i >> 2) * 2048 + (((i & 3) * 32 + lhi) ^ lsw), b0, b1, b2, b3);
          mma_bf16(cs[2 * (i & 3)], 0x3F803F80u, 0x3F803F80u, 0x3F803F80u, 0x3F803F80u, b0, b1);
          mma_bf16(cs[2 * (i & 3) + 1], 0x3F803F80u, 0x3F803F80u, 0x3F803F80u, 0x3F803F80u, b2, b3);
        }
        __syncwarp();
        if (el && n < 6) AUX_LOAD(n + 2);
        __syncwarp();
      }
      if (lane < 4) {
#pragma unroll
        for (int i = 0; i < 8; i++) st_b64(&g_colsum[rd >= 2][blk * 32 + i * 4 + lane][half], __float_as_uint(cs[i][0]), (__float_as_uint(cs[i][1]) & ~3u) | (ep1 & 3));
      }
      __syncwarp();
    }
  } else if (warp >= 8) {
    asm volatile("setmaxnreg.dec.sync.aligned.u32 40;");
    if (warp == 8) {
      const bool el = elect_one();
      cluster_wait();
      if (el) {
#pragma unroll 1
        for (int l = 0; l < NLAYERS; l++) {
          const uint32_t par = l & 1;
          const CUtensorMap* tqk = par ? &tm_wf : &tm_wqA;
          const CUtensorMap* tv = par ? &tm_wqB : &tm_wqA;
          const CUtensorMap* two = par ? &tm_woB : &tm_woA;
          if (l == 1) { LOAD_EPOCH(); wait_flag(&g_flags.wfready[jj].v, ep1 * 16); fence_proxy_async_global(); }
#pragma unroll 1
          for (int u = 0; u < 32; u++) {
            if (u >= 4) mbar_wait_sl(bar_done + (u - 4) * 8, par);
            else if (l) mbar_wait_sl(bar_done + (43 + u + (u >> 1)) * 8, par ^ 1);
            else if (u == 1) __nanosleep(STAG1);
            else if (u == 2) mbar_wait_sl(bar_full, 0);
            const uint32_t fb = bar_full + u * 8;
            const bool res = u < 4 ? (l || u >= 2) : (u < 11 || (u >= 18 && u < 22));
            mbar_expect_tx(fb, res ? QST : QST + SLOT);
            const int row = kslice(jj, u < 4 ? u & 1 : (u < 18 ? u - 2 : (u < 22 ? u - 6 : u - 20))) * 64 + (int)rank * 32;
            const int ps = u < 4 ? u >> 1 : (u >= 18), col = jj * 128 + ps * 64;
            const int c0 = par ? jj * 128 + (ps ? 0 : 1024) : col;
            const uint32_t dst = sbase + (u & 3) * QST + rank * 4096;
            tma_load_2d_mc(dst, tqk, fb, c0, row);
            tma_load_2d_mc(dst + 8192, tqk, fb, c0 + (par ? 64 : 1024), row);
            tma_load_2d_mc(dst + 16384, tv, fb, col + 2048, row);
            if (l == PRL && u >= PRU && u < PRU + 4) PROFT(473 + u - PRU);
          }
#pragma unroll 1
          for (int s = 0; s < 16; s++) {
            if (s < 5) { if (s != 2 && s != 4) mbar_wait_sl(bar_done + (28 + s) * 8, par); }
            else if (s != 14) mbar_wait_sl(bar_done + (27 + s - (s == 15)) * 8, par);
            const uint32_t fb = bar_full + (32 + s) * 8;
            mbar_expect_tx(fb, SLOT);
            tma_load_2d_mc(sbase + rank * 8192 + (uint32_t)((WO_BSLOT >> (4 * s)) & 15) * SLOT, two, fb, jj * 128 + (int)rank * 64, wslice(jj, s) * 64);
            const int ts = s + par;
            if (s >= 5 && ts < 8) {
              mbar_expect_tx(bar_chk - 8 + ts * 8, SLOT);
              tma_load_2d(sbase + (uint32_t)((WO_ASLOT(par) >> (4 * ts)) & 15) * SLOT, &tm_o, bar_chk - 8 + ts * 8, wslice(jj, ts) * 64, mm * 128);
            }
          }
        }
      }
      __syncwarp();
    } else if (warp == 9) {
      const bool el = elect_one();
      if (el) {
        PROFT(472);
        tma_load_2d(sbase + OFF_S, &tm_x0, bar_full, jj * 128, mm * 128);
        __nanosleep(STAG1);
        tma_load_2d(sbase + OFF_S + SLOT, &tm_x0, bar_full + 8, jj * 128 + 64, mm * 128);
      }
      __syncwarp();
      LOAD_EPOCH();
#pragma unroll 1
      for (int lp = 0; lp < 4 * NLAYERS; lp++) {
        const int l = lp >> 2, ph = lp & 3;
        if (ph == 3) continue;
        const uint32_t par = l & 1;
        const __nv_bfloat16* pb = g_obuf + (ph >> 1) * 64 + (size_t)(mm * 128 + (ph ? 0 : S_LEN) + (lane & 7) * 16 + (jj & 1) * 8) * D_MODEL + (jj >> 1) * 16;
        const CUtensorMap* tm = lp ? &tm_o : &tm_x0;
        const int row = mm * 128 + ((ph || !l) ? 0 : S_LEN);
        const uint32_t bit = ph ? O_BIT(l) : X_BIT(l - 1);
        const uint32_t slots = ph ? (uint32_t)(WO_ASLOT(par) >> (ph * 32 - 28)) : 0x8769876u;
        const unsigned long long fr = ph == 0 ? XPACE : ph == 1 ? (par ? 0x353535351Full : 0x35351F1Eull) : (par ? 0x27262524232232ull : 0x27262524233232ull);
        uint32_t rdy = (lp == 0 || (lp & 7) == 1) ? 0xFF : 0;
        mbar_wait_sl(ph ? bar_done + ((uint32_t)fr & 63) * 8 : (l ? bar_done + 47 * 8 : bar_full), ph ? par : (l ? par ^ 1 : 0));
#pragma unroll 1
        for (int i = 0; i < (ph == 1 ? 4 + par : 7); i++) {
          if (!((rdy >> i) & 1) && (i < NPOLL || ph == 1)) {
            const unsigned* pp = reinterpret_cast<const unsigned*>(pb + srcb(jj, i + ((lane >> 3) & (POLLW - 1)), ph) * 128);
            if (i == 0) __nanosleep(POLL0);
            unsigned v0 = ld_relaxed(pp);
            __nanosleep(POLLGAP);
            unsigned v1 = ld_relaxed(pp);
            uint32_t no;
#pragma unroll 1
            for (int it = 0; it < (1 << 18); it++) {
              no = __ballot_sync(0xffffffffu, (v0 ^ bit) & 1);
              if (!(no & 0xFF)) break;
              v0 = ld_relaxed(pp);
              no = __ballot_sync(0xffffffffu, (v1 ^ bit) & 1);
              if (!(no & 0xFF)) break;
              v1 = ld_relaxed(pp);
            }
            rdy = ((1 | (no & 0xFF00 ? 0 : 2) | (no & 0xFF0000 ? 0 : 4) | (no >> 24 ? 0 : 8)) & ((1 << POLLW) - 1)) << i;
          }
          if (ph || i >= XP0) mbar_wait_sl(bar_done + ((uint32_t)(fr >> (8 * i)) & 63) * 8, par);
          if (el) {
            if (i == 0) PROFT(320 + l * 16 + ph);
            const uint32_t cb = bar_chk + (ph >> 1) * 112 + i * 8;
            mbar_expect_tx(cb, SLOT);
            tma_load_2d(sbase + ((slots >> (4 * i)) & 15) * SLOT, tm, cb, srcb(jj, i, ph) * 128 + (ph >> 1) * 64, row);
          }
          __syncwarp();
        }
        if (ph == 0 && el) {
          if (l) { wait_flag(&g_flags.xready[l][mm].v, ep1 * 8); fence_proxy_async_global(); }
#pragma unroll 1
          for (int u = 11; u < 34; u++) {
            if (u == 18) u = 22;
            mbar_wait_sl(bar_done + (u - 4) * 8, par);
            if (u == 32) mbar_expect_tx(bar_xr, 2 * SLOT);
            tma_load_2d(sbase + OFF_RA + (u & 3) * SLOT, tm, u < 32 ? bar_full + u * 8 : bar_xr, kslice(jj, u < 18 ? u - 2 : (u < 32 ? u - 20 : u - 32)) * 64, row);
          }
        }
        __syncwarp();
      }
      cluster_wait();
    } else {
      const int hw = warp - 10;
      LOAD_EPOCH();
      const bool el = elect_one();
      cluster_wait();
      if (hw == 0) {
        mbar_wait_sl(bar_full + 8, 0);
        if (lane < 7) prefetch_tmap(lane == 0 ? &tm_os : lane == 1 ? &tm_o : lane == 2 ? &tm_wf : lane == 3 ? &tm_wqB : lane == 4 ? &tm_woA : lane == 5 ? &tm_woB : &tm_phi);
#pragma unroll 1
        for (int i = 0; i < (NLAYERS > 1 ? 9 : 0); i++) {
          if (i == 0 || i == 5) mbar_wait_sl(bar_done + (i >> 1) * 12, 0);
          if (el) {
            if (i == 0) { mbar_expect_tx(bar_phi, 2 * SLOT + 8192); tma_load_2d(sbase + OFF_PHI, &tm_phi, bar_phi, 0, jj * 128); }
            else tma_load_2d(sbase + (i > 4 ? 10 : 12) * SLOT - 4096 + i * 4096, &tm_wqB, bar_phi, (i > 4 ? 896 : 0) + jj * 128 + ((i - 1) >> 1) * 64, mm * 64 + (~i & 1) * 32);
          }
          __syncwarp();
          __nanosleep(PFGAP);
        }
      } else {
#pragma unroll 1
        for (int b = 0; b < 2; b++) {
          float4* z = reinterpret_cast<float4*>(g_kv[b] + (jj * 4) * KVH + mm * (4 * KVH / 16)) + lane;
#pragma unroll
          for (int i = 0; i < 6; i++) z[i * 32] = make_float4(0.f, 0.f, 0.f, 0.f);
        }
#pragma unroll 1
        for (int i = 0; i < 16; i++) {
          const int b = i >> 2;
          const uint32_t v = (b == 0 ? O_BIT(0) : b == 1 ? X_BIT(0) : H_BIT(0)) + 1;
          uint4* p = b < 2 ? reinterpret_cast<uint4*>(g_obuf + (size_t)(b * S_LEN + mm * 128 + (i & 3) * 32 + (lane >> 3) * 8) * D_MODEL + jj * 128 + (b ? 0 : 64)) + (lane & 7)
                           : g_halo + (size_t)(mm * 8 + jj) * 512 + i * 32 + lane;
          *p = make_uint4(v, v, v, v);
        }
        fence_proxy_async_global();
      }
      __syncwarp();
      uint32_t chkp = 0;
#pragma unroll 1
      for (int lp = 0; lp < 4 * NLAYERS; lp++) {
        const int l = lp >> 2, ph = (lp & 3) == 2 ? 2 - hw : (lp & 3);
        const uint32_t par = l & 1;
        int lane; asm volatile("mov.u32 %0, %%laneid;" : "=r"(lane));
        if ((lp & 3) == 2 || (hw && ph == 0)) {
          const uint32_t bit = ph ? O_BIT(l) : X_BIT(l - 1);
          uint32_t slots = ph ? (uint32_t)(WO_ASLOT(par) >> (ph * 32 - 28)) : 0x8769876u;
          const uint32_t a0 = sbase + (lane & 7) * 132 + (lane >> 3) * 32;
#pragma unroll 1
          for (int c = 0; c < 7; c++, slots >>= 4) {
            const uint32_t cb = bar_chk + 112 - hw * 112 + c * 8;
#pragma unroll 1
            for (int it = 0; it < (1 << 12); it++) {
              mbar_wait_sl(cb, (chkp >> c) & 1);
              chkp ^= 1u << c;
              if (el && c == 0) PROFT(ph == 1 ? 480 + l * 2 : 488 + l * 2 + (ph >> 1));
              if (lp == 0) break;
              uint32_t w[16];
#pragma unroll
              for (int i = 0; i < 16; i++) asm volatile("ld.shared.u32 %0, [%1];" : "=r"(w[i]) : "r"(a0 + (slots & 15) * SLOT + i * 1024) : "memory");
#pragma unroll
              for (int i = 0; i < 8; i++) w[i] = (w[i] ^ bit) | (w[i + 8] ^ bit);
              if (__all_sync(0xffffffffu, (((w[0] | w[1] | w[2]) | (w[3] | w[4] | w[5]) | (w[6] | w[7])) & 1) == 0)) break;
              if (el) {
                fence_proxy_async_smem();
                mbar_expect_tx(cb, SLOT);
                tma_load_2d(sbase + (slots & 15) * SLOT, &tm_o, cb, srcb(jj, c, ph) * 128 + (ph >> 1) * 64, mm * 128 + (ph ? 0 : S_LEN));
                RETRY_COUNT();
              }
              __syncwarp();
            }
            if (el) { mbar_arrive_local(bar_full + (c + (ph ? 25 + ph * 8 : 4)) * 8); if (lp == PRL * 4 && c == 0) PROFT(477); }
            __syncwarp();
          }
          if (ph) continue;
#pragma unroll 1
          for (int hp = 0; hp < 2; hp++) {
            const uint4* src = reinterpret_cast<const uint4*>(g_colsum[par][jj * 64 + hp * 32 + lane]);
            uint32_t bad;
            int it = 0;
            float c[6];
            do {
              bad = 0;
#pragma unroll
              for (int p = 0; p < 3; p++) {
                const uint4 v = ld_ll(src + ((par && p < 2) ? (hp ? -32 : 512) + p * 32 : p * 512));
                bad |= (v.y ^ ep1) | (v.w ^ ep1);
                c[2 * p] = __uint_as_float(v.x) + __uint_as_float(v.z); c[2 * p + 1] = __uint_as_float(v.y) + __uint_as_float(v.w);
              }
              bad &= 3;
              if (bad) __nanosleep(300);
            } while (bad && ++it < (1 << 16));
#pragma unroll
            for (int p = 0; p < 6; p++) {
              uint32_t h, m, lo;
              split3(c[p], h, m, lo);
              sts128(sbase + OFF_LNB + hp * 4096 + (p >> 1) * 1024 + lane * 32 + (p & 1) * 16, h | (m << 16), h | (lo << 16), h | (m << 16), lo | (m << 16));
            }
            fence_proxy_async_smem();
            __syncwarp();
            if (el) { mbar_arrive_local(hp ? bar_stat2 : bar_stat); if (hp == 0) PROFT(324 + l * 16); }
            __syncwarp();
          }
          continue;
        } else if (ph == 0) {
          mbar_wait_sl(bar_done + 24, par);
          const uint4* sp = reinterpret_cast<const uint4*>(g_stats + (size_t)(mm * 128) * 8) + lane;
#pragma unroll 1
          for (int hf = 0; hf < 4; hf++) {
            uint4 v[4];
            uint32_t bad;
            int it = 0;
            do {
              bad = 0;
#pragma unroll
              for (int i = 0; i < 4; i++) { v[i] = ld_ll(sp + (hf * 4 + i) * 32); bad |= (v[i].y ^ STAT_TAG(l)) | (v[i].w ^ STAT_TAG(l)); }
              bad &= 3;
              if (bad) __nanosleep(200);
            } while (bad && ++it < (1 << 16));
            __syncwarp();
            float mean = 0.f, m2 = 0.f;
#pragma unroll
            for (int i = 0; i < 4; i++) {
              float a = __uint_as_float(v[i].x) + __uint_as_float(v[i].z);
              a += __shfl_xor_sync(0xffffffffu, a, 1); a += __shfl_xor_sync(0xffffffffu, a, 2);
              a *= 0.125f;
              const float e0 = __uint_as_float(v[i].x) - a, e1 = __uint_as_float(v[i].z) - a;
              float q = fmaf(fmaf(e0, e0, e1 * e1), 128.f, __uint_as_float(v[i].y) + __uint_as_float(v[i].w));
              q += __shfl_xor_sync(0xffffffffu, q, 1); q += __shfl_xor_sync(0xffffffffu, q, 2);
              if ((lane & 3) == i) { mean = a; m2 = q; }
            }
            const uint32_t row = hf * 32 + (lane & 3) * 8 + (lane >> 2);
            uint32_t h, m, lo;
            split3(-0.5f * mean, h, m, lo);
            sts128(sbase + OFF_LNA + row * 16, h | (h << 16), m | (h << 16), lo | (m << 16), m | (lo << 16));
            sts32f(sbase + OFF_ST + row * 4, rsqrtf(m2 * (1.f / 1024.f) + 1e-5f));
          }
          fence_proxy_async_smem();
          __syncwarp();
          if (el) { mbar_arrive_local(bar_stat); PROFT(323 + l * 16); }
          __syncwarp();
#pragma unroll 1
          for (int i = 0; i < 8 - 4 * l; i++) {
            asm volatile("prefetch.global.L2 [%0];" :: "l"(i < 4 ? (l ? prm.wB_o : prm.wA_o) + (size_t)cta * 8192 + i * 2048 + lane * 64
                                                                 : prm.wB_qkv + (size_t)(cta * 8 + (i - 4) * 2 + (lane >> 4)) * 3072 + 2048 + (lane & 15) * 64));
            __nanosleep(PFGAP);
          }
          continue;
        }
        if (ph == 1) {
          if (par) continue;
#pragma unroll 1
          for (int i = 0; i < 2; i++) {
            if (i && lp + hw == 1 && NLAYERS > 1) {
#pragma unroll 1
              for (int c = 0; c < 8; c++) {
                if (!(c & 3)) asm volatile("bar.sync %0, 288;" :: "r"(BAR_WF + (c >> 2)) : "memory");
                if (el) {
                  tma_store_2d(&tm_wf, sbase + 11 * SLOT + c * 4096, (c < 4 ? 1024 : -128) + jj * 128 + (c >> 1) * 64, mm * 64 + (c & 1) * 32);
                  if ((c & 3) == 3) {
                    asm volatile("cp.async.bulk.commit_group;\ncp.async.bulk.wait_group.read 0;" ::: "memory");
                    mbar_arrive_local(bar_phi + (c >> 2) * 8);
                  } else __nanosleep(WFGAP);
                }
                __syncwarp();
              }
              if (el) { bulk_commit_wait(); signal_release(&g_flags.wfready[jj].v); PROFT(335); }
              __syncwarp();
            }
            mbar_wait_sl(bar_done + (i ? HW1 : (hw ? 19 : HW0)) * 8, 0);
            if (lp + hw == 2 && NLAYERS > 1) mbar_wait_sl(bar_phi, 1);
            const uint4* src = g_halo + (size_t)(mm * 8 + jj - 8) * 512 + i * 256 + hw * 128 + lane;
            uint4 v[4];
            int it = 0;
            bool ok;
            do {
#pragma unroll
              for (int j = 0; j < 4; j++) v[j] = mm ? ld_b128(src + j * 32) : make_uint4(H_BIT(l), 0, 0, 0);
              ok = __all_sync(0xffffffffu, (((v[0].x ^ H_BIT(l)) | (v[1].x ^ H_BIT(l)) | (v[2].x ^ H_BIT(l)) | (v[3].x ^ H_BIT(l))) & 1) == 0);
            } while (!ok && ++it < (1 << 16));
#pragma unroll
            for (int j = 0; j < 4; j++) sts128(sbase + OFF_S + hw * SLOT + j * 512 + lane * 16, v[j].x, v[j].y, v[j].z, v[j].w);
            __syncwarp();
            if (el) { mbar_arrive_local(bar_halo + hw * 8); PROFT(331 + l * 16 + i * 2 + hw); }
            __syncwarp();
          }
        } else if (hw == 0 && l < NLAYERS - 1) {
          bar_sync<BAR_X1, 288>();
          if (el) {
            PROFT(328 + l * 16);
            mbar_wait_sl(bar_full + XD * 8, par ^ 1);
            tma_store_2d(&tm_o, sbase + 11 * SLOT, jj * 128 + 64, mm * 128 + S_LEN);
            bulk_commit_wait();
            signal_release(&g_flags.xready[l + 1][mm].v);
            PROFT(330 + l * 16);
          }
          __syncwarp();
        }
      }
    }
    cluster_sync();
  } else {
    asm volatile("setmaxnreg.inc.sync.aligned.u32 232;");
    LOAD_EPOCH();
    const int wg = warp >> 2;
    const int r0 = warp * 16;
    const uint32_t pK = sbase + OFF_S, pV = sbase + OFF_S + SLOT;
#define PMASKS(on, bit) const uint32_t pm0 = ((on) && t == (g & 3) && (g >> 2) == (g & 1)), pm1 = ((on) && t == (g & 3) && (g >> 2) != (g & 1)), pbit = (bit)
#define PBIT0(w) (((w) & ~pm0) | (pbit & pm0))
#define PBIT1(w) (((w) & ~pm1) | (pbit & pm1))
#define LANE_CONSTS() \
    int lane; asm volatile("mov.u32 %0, %%laneid;" : "=r"(lane)); \
    const int g = lane >> 2, t = lane & 3; \
    const uint32_t srowoff = (r0 + (lane & 15)) * 128, lsw = (lane & 7) << 4, lhi = (lane >> 4) << 4, lsw2 = (lane & 6) << 3; \
    (void)g; (void)t; (void)srowoff; (void)lsw; (void)lhi; (void)lsw2;
    uint32_t stgp = 0, peer;
    asm volatile("mapa.shared::cluster.u32 %0, %1, %2;" : "=r"(peer) : "r"(sbase), "r"(rank ^ 1));
    peer -= sbase;
    const uint32_t dA0 = (((sbase & 0x3FFFF) + wg * 8192) >> 4) | 0x10000u, dB0 = ((sbase & 0x3FFFF) >> 4) | 0x2000000u;
    cluster_wait();
#define DESC(lo, hi) ((uint64_t)(uint32_t)(lo) | ((uint64_t)(hi) << 32))
#define STG_ARRIVE() { __syncwarp(); if (elect_one()) mbar_arrive_local(bar_stg); }
#define STG_WAIT() { mbar_wait(bar_stg, stgp); stgp ^= 1; }
#define PROFS() do {} while (0)
#define REL(addr) { if (elect_one()) { mbar_arrive_local(addr); asm volatile("mbarrier.arrive.shared::cluster.b64 _, [%0];" :: "r"((addr) + peer) : "memory"); } }
#define QSTEP(ACC, DA, SC, PRE) { \
      const uint32_t da = (DA), db = dB0 + (ub & 0x18) * (QST >> 7); \
      mbar_wait(ub, par); \
      PRE; \
      wgmma_fence(); \
      wgmma4_n192<SC>(ACC, da, db); \
      wgmma_commit(); PROFS(); }
#define QREL() { wgmma_wait<1>(); REL(ub + 376); ub += 8; }
#define RA_CUR (dA0 + (OFF_RA >> 4) + (ub & 0x18) * (SLOT >> 7))
#define PUMP1() { QSTEP(S1, RA_CUR, 1, {}); QREL(); }
#define PUMP0() { PUMP1(); SCHED_FENCE(); }
#define PUMP() if (h == 0) PUMP1()
#define WSTEP() { \
      const uint32_t s4 = (ub - bar_full - 256) >> 1; \
      const uint32_t da = dA0 + (((uint32_t)(WO_ASLOT(par) >> s4) & 15) << 10), db = dB0 + (((uint32_t)(WO_BSLOT >> s4) & 15) << 10); \
      mbar_wait(ub, par); \
      wgmma_fence(); \
      wgmma4_n128<1>(S1, da, db); \
      wgmma_commit(); PROFS(); \
      wgmma_wait<1>(); \
      if (s4) REL(ub + 376); \
      ub += 8; }
#define PUMPS(n) { _Pragma("unroll 1") for (int i_ = 0; i_ < (n); i_++) PUMP1(); }
#define SITE(n) { if ((BMASK >> (n)) & 1) PUMP1(); SCHED_FENCE(); }
#define LNSTEP(ACC, hh) { wgmma_fence(); wgmma_n192<1, 0>(ACC, make_desc(sbase + OFF_LNA + wg * 1024, 0, 128) ^ (1ull << 62), make_desc(sbase + OFF_LNB + (hh) * 4096, 0, 128) ^ (1ull << 62)); }
#define DRAIN_B(ACC) { \
      LANE_CONSTS(); \
      STAGE_V(ACC + 64, pV); \
      _Pragma("unroll") for (int i_ = 0; i_ < 64; i_++) st[i_] = ACC[i_]; \
      PIN(st, 64); }
#define WARP_STORE(tm, tile, col, row) { fence_proxy_async_smem(); __syncwarp(); \
      if (elect_one()) { tma_store_2d(tm, (tile) + r0 * 128, col, (row) + r0); asm volatile("cp.async.bulk.commit_group;" ::: "memory"); } __syncwarp(); }
#define PUBLISH_O() WARP_STORE(&tm_os, pO, jj * 128 + h * 64, mm * 128)
#define X_OUT(pc, on) { \
      PMASKS(on, X_BIT(l)); \
      _Pragma("unroll") for (int j = (pc) * 4; j < (pc) * 4 + 4; j++) \
        stsm_x4(pK + (pc) * SLOT + srowoff + ((((uint32_t)(j & 3) << 5) + lhi) ^ lsw), \
                PBIT0(pack_bf16(S1[j * 8 + 0], S1[j * 8 + 1])), PBIT0(pack_bf16(S1[j * 8 + 2], S1[j * 8 + 3])), \
                PBIT1(pack_bf16(S1[j * 8 + 4], S1[j * 8 + 5])), PBIT1(pack_bf16(S1[j * 8 + 6], S1[j * 8 + 7]))); }
#define REST_P1(SKEW) { \
      mbar_wait(bar_stat2, par); \
      LNSTEP(S1, 1); \
      _Pragma("unroll 1") while (ub < bar_full + 256) { \
        if (ub == bar_full + 256 - 8 * (SKEW) && wg == 0) bar_sync<BAR_SKEW, 256>(); \
        QSTEP(S1, RA_CUR, 1, {}); \
        if (ub == bar_full + 248 && wg == 1) bar_arrive<BAR_SKEW, 256>(); \
        QREL(); \
      } \
      mbar_wait(bar_done + (31 - (SKEW)) * 8, par);        \
      wgmma_wait<0>(); \
      ACC_FENCE(S1, 96); \
      REL(bar_done + 31 * 8); \
      PROF(13); }
#define FOLD(tile, rd) { \
          LANE_CONSTS(); \
          float d[32]; \
          ACC_DEF(d, 32); \
          mbar_wait(bar_phi, 0); \
          wgmma_fence(); \
          _Pragma("unroll") for (int i = 0; i < 2; i++) { \
            const uint64_t da = make_desc((tile) + wg * 8192 + i * 64, 16, 1024); \
            const uint64_t db = make_desc(sbase + OFF_PHI + wg * 4096 + i * 2048, 16, 512) ^ (3ull << 62); \
            wgmma_n32<0>(d + i * 16, da, db); wgmma_n32<1>(d + i * 16, da + 2, db + 64); \
          } \
          wgmma_commit(); \
          PUMP0(); \
          ACC_FENCE(d, 32); \
          bar_wg(wg); \
          _Pragma("unroll") for (int i = 0; i < 4; i++) { \
            const float* x = d + (i & 1) * 8 + (i >> 1) * 2; \
            if (rd) sts128((tile) + wg * 8192 + ((warp & 3) * 16 + (i >> 1) * 8 + g) * 128 + (((2 * t + (i & 1)) ^ g) << 4), \
                           pack_bf16(x[0], x[1]), pack_bf16(x[4], x[5]), pack_bf16(x[16], x[17]), pack_bf16(x[20], x[21])); \
            else stsm_x4((tile) + srowoff + ((((uint32_t)i << 5) + lhi) ^ lsw), pack_bf16(d[i * 8], d[i * 8 + 1]), pack_bf16(d[i * 8 + 2], d[i * 8 + 3]), \
                         pack_bf16(d[i * 8 + 4], d[i * 8 + 5]), pack_bf16(d[i * 8 + 6], d[i * 8 + 7])); \
          } \
          }
#define LOAD_X0(base) \
      _Pragma("unroll") for (int j = 0; j < 8; j++) { \
        uint32_t x0, x1, x2, x3; \
        ldsm_x4((base) + (j >> 2) * SLOT + srowoff + ((((uint32_t)(j & 3) << 5) + lhi) ^ lsw), x0, x1, x2, x3); \
        S1[j * 8 + 0] = bf_lo(x0); S1[j * 8 + 1] = bf_hi(x0); S1[j * 8 + 2] = bf_lo(x1); S1[j * 8 + 3] = bf_hi(x1); \
        S1[j * 8 + 4] = bf_lo(x2); S1[j * 8 + 5] = bf_hi(x2); S1[j * 8 + 6] = bf_lo(x3); S1[j * 8 + 7] = bf_hi(x3); \
      }
#define LOAD_X() { \
      wgmma_wait<0>(); \
      mbar_wait(bar_xr, par); \
      LOAD_X0(sbase + OFF_RA); \
      ACC_FENCE(S1, 64); \
      __syncwarp(); if (elect_one()) mbar_arrive_local(bar_lx); }

    float S1[96];
#pragma unroll
    for (int i = 0; i < 64; i++) S1[i] = 0.f;
#pragma unroll 1
    for (int l = 0; l < NLAYERS; l++) {
      const uint32_t par = l & 1;
      bar_wg(wg);
      PROF(0);
      uint32_t ub = bar_full;
      float S0[96];
      {
        LANE_CONSTS();
        ACC_DEF(S0, 96);
        QSTEP(S0, dA0 + (OFF_S >> 4), 0, {});
        ub += 8;
        PROF(1);
        if (l == 0) { mbar_wait(ub, 0); LOAD_X0(pK); }
        else { X_OUT(1, false); fence_proxy_async_smem(); }
        SCHED_FENCE();
        {
          float a0 = S1[0], a1 = S1[2], b0 = S1[1], b1 = S1[3];
#pragma unroll
          for (int i = 4; i < 64; i += 4) { a0 += S1[i]; b0 += S1[i + 1]; a1 += S1[i + 2]; b1 += S1[i + 3]; }
          a0 += b0; a1 += b1;
          a0 += __shfl_xor_sync(0xffffffffu, a0, 1); a1 += __shfl_xor_sync(0xffffffffu, a1, 1);
          a0 += __shfl_xor_sync(0xffffffffu, a0, 2); a1 += __shfl_xor_sync(0xffffffffu, a1, 2);
          a0 *= (1.f / 128.f); a1 *= (1.f / 128.f);
          asm volatile("" : "+f"(a0), "+f"(a1));
          bar_wg(wg);
          QSTEP(S0, dA0 + ((OFF_S + SLOT) >> 4), 1, wgmma_wait<0>());
          REL(ub + 376); ub += 8;
          SCHED_FENCE();
          float q0 = 0.f, q1 = 0.f;
          b0 = 0.f; b1 = 0.f;
#pragma unroll
          for (int i = 0; i < 64; i += 4) {
            const float d0 = S1[i] - a0, d1 = S1[i + 1] - a0, d2 = S1[i + 2] - a1, d3 = S1[i + 3] - a1;
            q0 = fmaf(d0, d0, q0); b0 = fmaf(d1, d1, b0); q1 = fmaf(d2, d2, q1); b1 = fmaf(d3, d3, b1);
          }
          q0 += b0; q1 += b1;
          q0 += __shfl_xor_sync(0xffffffffu, q0, 1); q1 += __shfl_xor_sync(0xffffffffu, q1, 1);
          q0 += __shfl_xor_sync(0xffffffffu, q0, 2); q1 += __shfl_xor_sync(0xffffffffu, q1, 2);
          if (t < 2) st_b64(g_stats + (size_t)(mm * 128 + r0 + g + t * 8) * 8 + jj, __float_as_uint(t ? a1 : a0), (__float_as_uint(t ? q1 : q0) & ~3u) | STAT_TAG(l));
        }
        if (l) { asm volatile("cp.async.bulk.wait_group 0;" ::: "memory"); bar_arrive<BAR_X1, 288>(); }
        ACC_DEF(S1, 96);
        QSTEP(S1, dA0 + (OFF_S >> 4), 0, {});
        QREL();
        QSTEP(S1, dA0 + ((OFF_S + SLOT) >> 4), 1, {});
        QREL();
#pragma unroll 1
        for (int i = 0; i < 14; i++) {
          QSTEP(S0, RA_CUR, 1, {});
          if (i == 0) PROF(2);
          QREL();
        }
      }
      LANE_CONSTS();
      mbar_wait(bar_stat, par);
      LNSTEP(S0, 0);
      wgmma_commit();
      const float rs0 = lds32f(sbase + OFF_ST + (r0 + g) * 4), rs1 = lds32f(sbase + OFF_ST + (r0 + g + 8) * 4);
      PUMP0();
      ACC_FENCE(S0, 96);
      PROF(3);
      if (!par) {
        constexpr uint32_t par = 0;
        uint32_t qa[16];
        uint32_t kf[32], vf[32];
#define DRAIN_A(ACC, hp, PMP) { \
          LANE_CONSTS(); \
          FRAG(kf + 16, ACC + 32, 0, (hp) * 2); \
          PMP; \
          FRAG(vf + 16, ACC + 64, 1, (hp) * 2 + 1); \
          _Pragma("unroll") for (int i_ = 0; i_ < 16; i_++) qa[i_] = pack_bf16(ACC[2 * i_], ACC[2 * i_ + 1]); \
          PINU(qa, 16); }
        DRAIN_A(S0, 0, PUMP0());
        if (l == 0 && NLAYERS > 1) {
#pragma unroll 1
          for (int rd = 1; rd >= 0; rd--) {
            FOLD(sbase + (12 - rd) * SLOT, rd);
            fence_proxy_async_smem();
            asm volatile("bar.arrive %0, 288;" :: "r"(BAR_WF + 1 - rd) : "memory");
          }
        }
        PUMPS(FPUMP);
        if (l == 0 && NLAYERS > 1) mbar_wait(bar_phi, 1);
#pragma unroll 1
        for (int h = 0; h < 2; h++) {
          const uint32_t pO = sbase + (h ? 3 : 12) * SLOT;
          PROF(4 + h * 12);
          LANE_CONSTS();
          FRAG_PUT(kf + 16, 10); FRAG_PUT(vf + 16, 11);
          STG_ARRIVE();
          if (h) { LOAD_X(); if (AW0) WSTEP(); } else PUMPS(HPUMP2);
          STG_WAIT();
          if (warp == 0) mbar_wait(bar_halo, h);
          FRAG_GET(kf, 10);
          PROF(5 + h * 12);
          float s[2][4][4];
#pragma unroll
          for (int ks = 0; ks < 2; ks++)
#pragma unroll
            for (int i = 0; i < 8; i++) {
              const int hh = (i >> 1) & 1, jb = (i & 1) + (~i >> 1 & 2);
              const uint32_t* b = kf + (jb >> 1) * 16 + hh * 8 + ks * 4 + (jb & 1) * 2;
              if (ks) mma_bf16(s[hh][jb], qa[hh * 8 + 4], qa[hh * 8 + 5], qa[hh * 8 + 6], qa[hh * 8 + 7], b[0], b[1]);
              else mma_bf16_z(s[hh][jb], qa[hh * 8], qa[hh * 8 + 1], qa[hh * 8 + 2], qa[hh * 8 + 3], b[0], b[1]);
            }
          PUMP();
          PROF(6 + h * 12);
          const bool e = g & 1, hb = (2 * t + (g & 1)) <= g;
          float va[2][2], vb[2][2], mx[2][2];
#pragma unroll
          for (int hh = 0; hh < 2; hh++) {
            va[hh][0] = e ? s[hh][1][1] : s[hh][1][0];
            vb[hh][0] = hb ? (e ? s[hh][2][1] : s[hh][2][0]) : (e ? s[hh][0][1] : s[hh][0][0]);
            va[hh][1] = e ? s[hh][2][3] : s[hh][2][2];
            vb[hh][1] = hb ? (e ? s[hh][3][3] : s[hh][3][2]) : (e ? s[hh][1][3] : s[hh][1][2]);
          }
          if (warp == 0 && mm == 0) {
#pragma unroll
            for (int hh = 0; hh < 2; hh++) { va[hh][0] = -INFINITY; if (!hb) { vb[hh][0] = -INFINITY; vb[hh][1] = -INFINITY; } }
          }
#pragma unroll
          for (int i = 0; i < 4; i++) mx[i >> 1][i & 1] = fmaxf(va[i >> 1][i & 1], vb[i >> 1][i & 1]);
#pragma unroll
          for (int o = 1; o <= 2; o <<= 1)
#pragma unroll
            for (int i = 0; i < 4; i++) mx[i >> 1][i & 1] = fmaxf(mx[i >> 1][i & 1], __shfl_xor_sync(0xffffffffu, mx[i >> 1][i & 1], o));
          const float sc0 = rs0 * (0.17677669529663687f * LOG2E), sc1 = rs1 * (0.17677669529663687f * LOG2E);
#pragma unroll
          for (int i = 0; i < 4; i++) {
            const float sc = (i & 1) ? sc1 : sc0, m = mx[i >> 1][i & 1];
            va[i >> 1][i & 1] = ex2((va[i >> 1][i & 1] - m) * sc); vb[i >> 1][i & 1] = ex2((vb[i >> 1][i & 1] - m) * sc);
            mx[i >> 1][i & 1] = va[i >> 1][i & 1] + vb[i >> 1][i & 1];
          }
          if (h == 0 && ASITE) { PIN(&va[0][0], 4); PIN(&vb[0][0], 4); PIN(&mx[0][0], 4); PUMP1(); }
          if (warp == 0) mbar_wait(bar_halo + 8, h);
          FRAG_GET(vf, 11);
#pragma unroll
          for (int o = 1; o <= 2; o <<= 1)
#pragma unroll
            for (int i = 0; i < 4; i++) mx[i >> 1][i & 1] += __shfl_xor_sync(0xffffffffu, mx[i >> 1][i & 1], o);
          const uint32_t selA = e ? 0x1044 : 0x4410, selB = e ? 0x3244 : 0x4432, selL = hb ? 0x4444 : selB, selH = hb ? selB : 0x4444;
          float o[2][4][4];
          uint32_t pa[2][8];
#pragma unroll
          for (int hh = 0; hh < 2; hh++) {
            const float i0 = rcp_fast(mx[hh][0]), i1 = rcp_fast(mx[hh][1]);
            const uint32_t w0 = pack_bf16(va[hh][0] * i0, vb[hh][0] * i0), w1 = pack_bf16(va[hh][1] * i1, vb[hh][1] * i1);
            pa[hh][0] = __byte_perm(w0, 0, selL); pa[hh][2] = __byte_perm(w0, 0, selA); pa[hh][3] = __byte_perm(w1, 0, selL);
            pa[hh][4] = __byte_perm(w0, 0, selH); pa[hh][5] = __byte_perm(w1, 0, selA); pa[hh][7] = __byte_perm(w1, 0, selH);
            pa[hh][1] = pa[hh][0] & pa[hh][4]; pa[hh][6] = pa[hh][3] & pa[hh][7];
          }
          PROF(7 + h * 12);
#pragma unroll
          for (int i = 0; i < 8; i++) mma_bf16_z(o[i >> 2][i & 3], pa[i >> 2][4], pa[i >> 2][5], pa[i >> 2][6], pa[i >> 2][7], vf[16 + 2 * i], vf[17 + 2 * i]);
#pragma unroll
          for (int i = 0; i < 8; i++) mma_bf16(o[i >> 2][i & 3], pa[i >> 2][0], pa[i >> 2][1], pa[i >> 2][2], pa[i >> 2][3], vf[2 * i], vf[2 * i + 1]);
          if (h == 0) PUMP1() else mbar_wait(bar_done + 30 * 8, par);
          if (NLAYERS > 1) mbar_wait(bar_phi + 8, 0);
#pragma unroll
          for (int i = 0; i < 4; i++) {
            const int hh = i >> 1, dp = i & 1;
            PMASKS(true, O_BIT(l));
            stsm_x4(pO + srowoff + ((hh * 64 + dp * 32 + lhi) ^ lsw), PBIT0(pack_bf16(o[hh][dp * 2][0], o[hh][dp * 2][1])), PBIT0(pack_bf16(o[hh][dp * 2][2], o[hh][dp * 2][3])),
                    PBIT1(pack_bf16(o[hh][dp * 2 + 1][0], o[hh][dp * 2 + 1][1])), PBIT1(pack_bf16(o[hh][dp * 2 + 1][2], o[hh][dp * 2 + 1][3])));
          }
          PUBLISH_O();
          PROF(11 + h * 12);
          if (h) break;
          REST_P1(ASKEW);
          asm volatile("cp.async.bulk.wait_group.read 0;" ::: "memory");
          DRAIN_A(S1, 1, {});
        }
      } else {
        constexpr uint32_t par = 1;
        float st[64];
        DRAIN_B(S0);
        if (warp < 2) sts128(sbase + OFF_ONES + warp * 512 + lane * 16, 0x3F803F80u, 0x3F803F80u, 0x3F803F80u, 0x3F803F80u);
        const float c0 = rs0 * LOG2E, c1 = rs1 * LOG2E;
#define KV_MMA(vs) { \
          const uint32_t dp = dA0 + 12 * 1024 - wg * 2560, dv = dA0 + (vs) * 1024 + ((OFF_ONES - (vs) * SLOT - 16) << 12) - wg * (512 << 16); \
          STG_WAIT(); \
          wgmma_fence(); \
          _Pragma("unroll") for (int ks = 0; ks < 8; ks++) { \
            const uint64_t a = DESC(dp + ks * 128, 0x40000040), b = DESC(dv + ks * (64 - (64 << 16)), 0x80000020); \
            if (ks == 0) wgmma_n40<0, 1>(kv, a, b); else wgmma_n40<1, 1>(kv, a, b); } \
          wgmma_commit(); }
#define KV_RED(hp) { \
          float* kvg = g_kv[l >> 1] + (jj * 4 + (hp) * 2 + wg) * KVH + ((warp & 3) * 32 + lane) * 4; \
          _Pragma("unroll") for (int i = 0; i < 5; i++) red_v4(kvg + i * 512, kv[i * 3], kv[i * 3 + 1], kv[i * 3 + 2], 1.f); \
          red_v4(kvg + 2560, kv[15], kv[16], kv[18], 1.f); }
#define KV_LOAD(hp) { \
          const uint4* kvg = reinterpret_cast<const uint4*>(g_kv[l >> 1] + (jj * 4 + (hp) * 2 + wg) * KVH) + (warp & 3) * 32 + lane; \
          _Pragma("unroll") for (int i = 0; i < 6; i++) v[i] = ld_b128(kvg + i * 128); }
#define KVV(i) __uint_as_float((i) % 3 == 0 ? v[(i) / 3].x : ((i) % 3 == 1 ? v[(i) / 3].y : v[(i) / 3].z))
#define KV_TILE(hp) { \
          _Pragma("unroll 1") for (int it = 0; it < (1 << 16); it++) { \
            if (__all_sync(0xffffffffu, (v[0].w & v[1].w & v[2].w & v[3].w & v[4].w & v[5].w) == 0x41800000u)) break; \
            RETRY_COUNT(); \
            KV_LOAD(hp); \
          } \
          PROF(25 + (hp)); \
          const uint32_t e = lane & 7, jt = ((lane >> 1) & 4) + (e >> 1); \
          const uint32_t row = ((((warp >> 1) ^ wg) & 1) << 5) + ((jt & 1) << 4) + ((warp & 1) << 3) + (jt & 6) + (e & 1); \
          const uint32_t kd = pV + wg * 8192 + row * 128, ksw = (row & 7) << 4; \
          _Pragma("unroll") for (int i = 0; i < 2; i++) \
            stsm_x4(kd + ((i * 32 + lhi) ^ ksw), pack_bf16(KVV(i * 8), KVV(i * 8 + 1)), pack_bf16(KVV(i * 8 + 2), KVV(i * 8 + 3)), \
                    pack_bf16(KVV(i * 8 + 4), KVV(i * 8 + 5)), pack_bf16(KVV(i * 8 + 6), KVV(i * 8 + 7))); \
          stsm_x4(kd + ((64u + lhi) ^ ksw), pack_bf16(KVV(16), 1.f), pack_bf16(KVV(17), 1.f), 0u, 0u); }
#pragma unroll 1
        for (int h = 0; h < 2; h++) {
          PROF(4 + h * 2);
          SITE(0);
          LANE_CONSTS();
          const uint32_t dsw = (uint32_t)(g ^ (2 * t)) << 4, dst = ((t & 2) ? pK : sbase + 12 * SLOT) + (r0 + g) * 128;
          float e[16], f[16];
          float mn0 = rmin16(st);
          asm volatile("" : "+f"(mn0)); SCHED_FENCE();
          float sa = exps16(e, st, -c0, mn0 * c0), mx0 = rmax16(st);
          asm volatile("" : "+f"(sa), "+f"(mx0)); PIN(e, 16); SITE(1);
          if (h) STG_WAIT();
          store16(e, sa, dst, dsw, 4);
          float sb = exps16(f, st, c0, -mx0 * c0), mn1 = rmin16(st + 2);
          asm volatile("" : "+f"(sb), "+f"(mn1)); PIN(f, 16); SITE(2);
          store16(f, sb, dst, dsw, 0);
          float sc = exps16(e, st + 2, -c1, mn1 * c1), mx1 = rmax16(st + 2);
          asm volatile("" : "+f"(sc), "+f"(mx1)); PIN(e, 16); SITE(3);
          store16(e, sc, dst + 1024, dsw, 4);
          float sd = exps16(f, st + 2, c1, -mx1 * c1);
          asm volatile("" : "+f"(sd)); PIN(f, 16); SITE(4);
          store16(f, sd, dst + 1024, dsw, 0);
          PROF(5 + h * 2);
          if (h) break;
          {
            float kv[20];
            ACC_DEF(kv, 20);
            fence_proxy_async_smem();
            STG_ARRIVE();
            KV_MMA(11);
            PUMP0();
            ACC_FENCE(kv, 20);
            KV_RED(0);
            STG_ARRIVE();
          }
#pragma unroll
          for (int i = 0; i < 32; i++) st[i] = st[32 + i];
        }
        float mq[8];
        uint4 v[6];
        {
          float kv[20];
          mbar_wait(bar_stat2, par);
          LNSTEP(S1, 1);
          ub = bar_full + 240;
          PUMP1();
          if (wg == 0) bar_sync<BAR_SKEW, 256>();
          QSTEP(S1, RA_CUR, 1, {});
          if (wg == 1) bar_arrive<BAR_SKEW, 256>();
          QREL();
          mbar_wait(bar_done + 30 * 8, par);
          wgmma_wait<0>();
          ACC_FENCE(S1, 96);
          if (!(RLATE & 2)) REL(bar_done + 31 * 8);
          PROF(13);
          LANE_CONSTS();
          STAGE_V(S1 + 64, sbase + 3 * SLOT);
          fence_proxy_async_smem();
          STG_ARRIVE();
          if (RLATE & 2) REL(bar_done + 31 * 8);
#pragma unroll
          for (int i = 0; i < 32; i++) st[i] = S1[i];
          PIN(st, 32);
          PROF(16);
          ACC_DEF(kv, 20);
          KV_MMA(3);
          SCHED_FENCE();
          KV_LOAD(0);
          extrema(mq, st, c0, c1);
          PIN(mq, 8);
          SCHED_FENCE();
          wgmma_wait<0>();
          ACC_FENCE(kv, 20);
          KV_RED(1);
          PROF(17);
        }
#pragma unroll 1
        for (int h = 0; h < 2; h++) {
          const uint32_t pO = sbase + (h ? 3 : 8) * SLOT;
          LANE_CONSTS();
          uint32_t fq[32];
          expp16(fq, st, -c0, mq[0], -c1, mq[1]); expp16(fq + 8, st, c0, mq[2], c1, mq[3]); PINU(fq, 16);
          PROF(18 + h * 14);
          SCHED_FENCE();
          if (h) {
            asm volatile("cp.async.bulk.wait_group.read 0;" ::: "memory");
            mbar_wait(bar_lx, par);
          }
          KV_TILE(h);
          fence_proxy_async_smem();
          STG_ARRIVE();
          SCHED_FENCE();
          expp16(fq + 16, st + 16, -c0, mq[4], -c1, mq[5]); PINU(fq + 16, 8);
          STG_WAIT();
          wgmma_wait<0>();
          ACC_FENCE(S1, 64);
          PROF(19 + h * 14);
          float o[4][20];
#define O_MMA(hh) { \
            const uint64_t db = make_desc(pV + (hh) * 8192, 16, 1024); \
            ACC_DEF(o[(hh) * 2], 20); ACC_DEF(o[(hh) * 2 + 1], 20); \
            wgmma_fence(); \
            wgmma_n40_rs<0>(o[(hh) * 2], fq + (hh) * 16, db + 256); wgmma_n40_rs<0>(o[(hh) * 2 + 1], fq + (hh) * 16 + 8, db); \
            wgmma_n40_rs<1>(o[(hh) * 2], fq + (hh) * 16 + 4, db + 384); wgmma_n40_rs<1>(o[(hh) * 2 + 1], fq + (hh) * 16 + 12, db + 128); \
            wgmma_commit(); }
          O_MMA(0);
          SCHED_FENCE();
          expp16(fq + 24, st + 16, c0, mq[6], c1, mq[7]); PINU(fq + 24, 8);
          SCHED_FENCE();
          PMASKS(true, O_BIT(l));
#pragma unroll
          for (int hh = 0; hh < 2; hh++) {
            if (hh && !OW) O_MMA(1);
            wgmma_wait<0>();
            ACC_FENCE(o[hh * 2], 20); ACC_FENCE(o[hh * 2 + 1], 20);
            if (!hh && OW) { O_MMA(1); SCHED_FENCE(); }
            const float* x = o[hh * 2];
            const float* y = o[hh * 2 + 1];
            const float rx0 = rcp_fast(x[17]), ry0 = rcp_fast(y[17]), rx1 = rcp_fast(x[19]), ry1 = rcp_fast(y[19]);
            const float i0 = rcp_fast(fmaf(x[16], rx0, y[16] * ry0) + 1e-6f), i1 = rcp_fast(fmaf(x[18], rx1, y[18] * ry1) + 1e-6f);
            const float ax0 = rx0 * i0, ay0 = ry0 * i0, ax1 = rx1 * i1, ay1 = ry1 * i1;
#pragma unroll
            for (int dp = 0; dp < 2; dp++)
              stsm_x4(pO + srowoff + ((hh * 64 + dp * 32 + lhi) ^ lsw),
                      PBIT0(pack_bf16(fmaf(x[dp * 8], ax0, y[dp * 8] * ay0), fmaf(x[dp * 8 + 1], ax0, y[dp * 8 + 1] * ay0))),
                      PBIT0(pack_bf16(fmaf(x[dp * 8 + 2], ax1, y[dp * 8 + 2] * ay1), fmaf(x[dp * 8 + 3], ax1, y[dp * 8 + 3] * ay1))),
                      PBIT1(pack_bf16(fmaf(x[dp * 8 + 4], ax0, y[dp * 8 + 4] * ay0), fmaf(x[dp * 8 + 5], ax0, y[dp * 8 + 5] * ay0))),
                      PBIT1(pack_bf16(fmaf(x[dp * 8 + 6], ax1, y[dp * 8 + 6] * ay1), fmaf(x[dp * 8 + 7], ax1, y[dp * 8 + 7] * ay1))));
          }
          PUBLISH_O();
          PROF(20 + h * 14);
          if (h) break;
#pragma unroll
          for (int i = 0; i < 32; i++) st[i] = S1[32 + i];
          PIN(st, 32);
          LOAD_X();
          bar_wg(wg);
          WSTEP();
          SCHED_FENCE();
          if (KVL == 0) KV_LOAD(1);
          extrema(mq, st, c0, c1);
          PIN(mq, 8);
          if (KVL == 1) { SCHED_FENCE(); KV_LOAD(1); }
          PROF(31);
        }
      }
      __syncwarp();
      if (elect_one()) mbar_arrive_local(bar_epi);
      bar_wg(wg);
#pragma unroll 1
      while (ub < bar_full + 384) {
        WSTEP();
        if (ub == bar_full + 8 * 41) { asm volatile("cp.async.bulk.wait_group.read 0;" ::: "memory"); PROF(35); }
        if (ub == bar_full + 8 * 42) PROF(36);
      }
      wgmma_wait<0>();
      ACC_FENCE(S1, 64);
      if (!RLATE) REL(bar_done + 47 * 8);
      PROF(37);
      {
        LANE_CONSTS();
        X_OUT(0, l < NLAYERS - 1);
        WARP_STORE(l < NLAYERS - 1 ? &tm_os : &tm_xo, pK, jj * 128, mm * 128 + (l < NLAYERS - 1 ? S_LEN : 0));
        if (RLATE) REL(bar_done + 47 * 8);
        if (l == NLAYERS - 1) {
          X_OUT(1, false);
          WARP_STORE(&tm_xo, pV, jj * 128 + 64, mm * 128);
          asm volatile("cp.async.bulk.wait_group 0;" ::: "memory");
        }
      }
#pragma unroll
      for (int i = 32; i < 64; i++) { uint32_t c; asm volatile("mov.b32 %0, %1;" : "=r"(c) : "f"(S1[i])); S1[i] = __uint_as_float(c); }
      PROF(38);
    }
    const int tid = threadIdx.x;
    if (tid == 0) {
      unsigned old = atomicAdd(&g_flags.done.v, 1);
      if (old == ep1 * NMAIN - 1) {
        asm volatile("st.relaxed.gpu.global.u32 [%0], %1;" :: "l"(&g_flags.epoch.v), "r"(ep1) : "memory");
      }
    }
    __syncwarp();
    cluster_sync();
  }
}

typedef CUresult (*PFN_encode)(CUtensorMap*, CUtensorMapDataType, cuuint32_t, void*, const cuuint64_t*, const cuuint64_t*,
                               const cuuint32_t*, const cuuint32_t*, CUtensorMapInterleave, CUtensorMapSwizzle,
                               CUtensorMapL2promotion, CUtensorMapFloatOOBfill);

CUtensorMap make_map(PFN_encode enc, const void* ptr, uint64_t inner, uint64_t outer, uint32_t box_inner, uint32_t box_outer,
                     CUtensorMapSwizzle swz = CU_TENSOR_MAP_SWIZZLE_128B) {
  CUtensorMap m;
  cuuint64_t dims[2] = {inner, outer};
  cuuint64_t strides[1] = {inner * 2};
  cuuint32_t box[2] = {box_inner, box_outer};
  cuuint32_t es[2] = {1, 1};
  enc(&m, CU_TENSOR_MAP_DATA_TYPE_BFLOAT16, 2, const_cast<void*>(ptr), dims, strides, box, es, CU_TENSOR_MAP_INTERLEAVE_NONE,
      swz, CU_TENSOR_MAP_L2_PROMOTION_L2_256B, CU_TENSOR_MAP_FLOAT_OOB_FILL_NONE);
  return m;
}

}

extern "C" void kernel_launch(void* const* d_in, const int* in_sizes, int n_in, void* d_out, int out_size) {
  (void)in_sizes; (void)n_in; (void)out_size;
  static PFN_encode enc = nullptr;
  if (!enc) {
    void* fn = nullptr;
    cudaDriverEntryPointQueryResult qr;
    cudaGetDriverEntryPoint("cuTensorMapEncodeTiled", &fn, cudaEnableDefault, &qr);
    enc = (PFN_encode)fn;
    cudaFuncSetAttribute(mega_kernel, cudaFuncAttributeMaxDynamicSharedMemorySize, SMEM_BYTES);
  }
  Params prm;
  prm.x0 = (const __nv_bfloat16*)d_in[0];
  prm.wA_qkv = (const __nv_bfloat16*)d_in[1];
  prm.wA_o = (const __nv_bfloat16*)d_in[2];
  prm.wB_qkv = (const __nv_bfloat16*)d_in[4];
  prm.wB_phi = (const __nv_bfloat16*)d_in[5];
  prm.wB_o = (const __nv_bfloat16*)d_in[6];
  prm.out = (__nv_bfloat16*)d_out;
  void *obuf = nullptr, *wf = nullptr;
  cudaGetSymbolAddress(&obuf, g_obuf);
  cudaGetSymbolAddress(&wf, g_wfold);
  CUtensorMap tm_x0 = make_map(enc, d_in[0], D_MODEL, S_LEN, 64, 128);
  CUtensorMap tm_xo = make_map(enc, d_out, D_MODEL, S_LEN, 64, 16);
  CUtensorMap tm_os = make_map(enc, obuf, D_MODEL, 2 * S_LEN, 64, 16);
  CUtensorMap tm_o = make_map(enc, obuf, D_MODEL, 2 * S_LEN, 64, 128);
  CUtensorMap tm_wf = make_map(enc, wf, 2048, D_MODEL, 64, 32);
  CUtensorMap tm_wqA = make_map(enc, d_in[1], 3 * D_MODEL, D_MODEL, 64, 32);
  CUtensorMap tm_wqB = make_map(enc, prm.wB_qkv, 3 * D_MODEL, D_MODEL, 64, 32);
  CUtensorMap tm_woA = make_map(enc, prm.wA_o, D_MODEL, D_MODEL, 64, 64);
  CUtensorMap tm_woB = make_map(enc, prm.wB_o, D_MODEL, D_MODEL, 64, 64);
  CUtensorMap tm_phi = make_map(enc, prm.wB_phi, 32, 1024, 32, 128, CU_TENSOR_MAP_SWIZZLE_64B);
  mega_kernel<<<NMAIN + NAUX, 384, SMEM_BYTES>>>(tm_x0, tm_xo, tm_os, tm_o, tm_wf, tm_wqA, tm_wqB, tm_woA, tm_woB, tm_phi, prm);
}
```

```cpp
#include <cuda_runtime.h>
#include <cuda.h>
#include <cuda_bf16.h>
#include <stdint.h>

#define NLAYERS 4

#define STAG1 300
#define HPUMP1 2
#define HPUMP2 1
#define ASKEW 2
#define FPUMP 3
#define PFGAP 100
#define POLLW 4
#define POLL0 0
#define POLLGAP 120
#define OW 1
#define NPOLL 4
#define AW0 1
#define RLATE 3
#define FSTART 0
#define MAPV 1
#define HW1 29
#define XPACE 0x06050401000000ull
#define XP0 4
#define HW0 18
#define XD 4
#define WFGAP 50
#define KVL 1
#define BMASK 0x1F
#define ASITE 1
namespace {

constexpr int S_LEN = 2048, D_MODEL = 1024;
constexpr int NAUX = 4, NMAIN = 128;
constexpr int SLOT = 16384;
constexpr int QST = 24576;
constexpr int OFF_RA = 6 * SLOT, OFF_S = 10 * SLOT;
constexpr int OFF_HALO = 13 * SLOT, OFF_LNB = OFF_HALO  , OFF_ONES = OFF_HALO + 3072;
constexpr int OFF_ST = OFF_HALO + 7168  , OFF_PHI = OFF_HALO + 8192;
constexpr int OFF_BAR = 14 * SLOT;
constexpr int OFF_LNA = OFF_BAR + 1024;
constexpr int SMEM_BYTES = OFF_LNA + 2048;
#define WO_ASLOT(par) ((par) ? 0x9876CAB39876CA98ull : 0x98C76BA398C7698Cull)
constexpr unsigned long long WO_BSLOT = 0x5432105421054210ull;
__device__ __forceinline__ int srcb(int j, int i) { return (i + (i >= j)) & 7; }
__device__ __forceinline__ int kslice(int j, int i) { return i < 2 ? 2 * j + i : (i < 9 ? 2 * srcb(j, i - 2) : 2 * srcb(j, i - 9) + 1); }
__device__ __forceinline__ int wslice(int j, int s) { return 2 * ((s & 7) ? srcb(j, (s & 7) - 1) : j) + (s >> 3); }
constexpr int KVH = 6 * 128 * 4;

struct __align__(128) Flag { unsigned v; unsigned pad[31]; };
struct Flags {
  Flag xready[4][16];
  Flag wfready[8];
  Flag done;
  Flag epoch;
};

__device__ Flags g_flags;
__device__ __nv_bfloat16 g_obuf[2 * S_LEN * D_MODEL];
#define O_BIT(l) ((epoch * NLAYERS + (l) + 1) & 1u)
#define X_BIT(l) ((epoch * (NLAYERS - 1) + (l) + 1) & 1u)
__device__ __nv_bfloat16 g_wfold[D_MODEL * 2048];
__device__ uint4 g_halo[16 * 8 * 512];
__device__ __align__(128) float g_kv[2][32 * KVH];
__device__ __align__(128) uint2 g_colsum[2][1536][2];
__device__ __align__(128) uint2 g_stats[S_LEN * 8];
#define H_BIT(l) (NLAYERS > 2 ? (uint32_t)((l) == 0) : (ep1 & 1))
#define STAT_TAG(l) ((ep1 * NLAYERS + (l) + 1) & 3u)

#define RETRY_COUNT()
#define PRL 0
#define PRU 0
#define PROFL 1
#define PROFW 0
#define PROFT(i) do {} while (0)
#define PROF(i) do {} while (0)

__device__ __forceinline__ uint32_t smem_u32(const void* p) { return (uint32_t)__cvta_generic_to_shared(p); }
__device__ __forceinline__ bool elect_one() {
  uint32_t p;
  asm volatile("{\n.reg .pred p;\nelect.sync _|p, 0xffffffff;\nselp.u32 %0, 1, 0, p;\n}\n" : "=r"(p));
  return p != 0;
}
__device__ __forceinline__ void mbar_init(uint32_t bar, uint32_t cnt) {
  asm volatile("mbarrier.init.shared::cta.b64 [%0], %1;" :: "r"(bar), "r"(cnt));
}
__device__ __forceinline__ void mbar_expect_tx(uint32_t bar, uint32_t bytes) {
  asm volatile("mbarrier.arrive.expect_tx.shared::cta.b64 _, [%0], %1;" :: "r"(bar), "r"(bytes) : "memory");
}
#define mbar_wait(bar, parity) \
  asm volatile("{\n.reg .pred p, q;\nW_%=:\nmbarrier.try_wait.parity.shared::cta.b64 p, [%1], %2;\nadd.s32 %0, %0, -1;\n" \
               "setp.gt.and.s32 q, %0, 0, !p;\n@q bra.uni W_%=;\n}\n" : "+r"(budget) : "r"((uint32_t)(bar)), "r"((uint32_t)(parity)) : "memory")
#define mbar_wait_sl(bar, parity) \
  asm volatile("{\n.reg .pred p, q;\nW_%=:\nmbarrier.try_wait.parity.shared::cta.b64 p, [%1], %2, 20000;\nadd.s32 %0, %0, -64;\n" \
               "setp.gt.and.s32 q, %0, 0, !p;\n@q bra.uni W_%=;\n}\n" : "+r"(budget) : "r"((uint32_t)(bar)), "r"((uint32_t)(parity)) : "memory")
__device__ __forceinline__ void mbar_arrive_local(uint32_t bar) {
  asm volatile("mbarrier.arrive.shared::cta.b64 _, [%0];" :: "r"(bar) : "memory");
}
__device__ __forceinline__ void tma_load_2d(uint32_t dst, const CUtensorMap* tm, uint32_t bar, int c0, int c1) {
  asm volatile("cp.async.bulk.tensor.2d.shared::cluster.global.mbarrier::complete_tx::bytes [%0], [%1, {%3, %4}], [%2];"
               :: "r"(dst), "l"(tm), "r"(bar), "r"(c0), "r"(c1) : "memory");
}
__device__ __forceinline__ void tma_load_2d_mc(uint32_t dst, const CUtensorMap* tm, uint32_t bar, int c0, int c1) {
  asm volatile("cp.async.bulk.tensor.2d.shared::cluster.global.mbarrier::complete_tx::bytes.multicast::cluster [%0], [%1, {%3, %4}], [%2], %5;"
               :: "r"(dst), "l"(tm), "r"(bar), "r"(c0), "r"(c1), "h"((uint16_t)3) : "memory");
}
__device__ __forceinline__ void tma_store_2d(const CUtensorMap* tm, uint32_t src, int c0, int c1) {
  asm volatile("cp.async.bulk.tensor.2d.global.shared::cta.bulk_group [%0, {%2, %3}], [%1];"
               :: "l"(tm), "r"(src), "r"(c0), "r"(c1) : "memory");
}
__device__ __forceinline__ void bulk_commit_wait() {
  asm volatile("cp.async.bulk.commit_group;\ncp.async.bulk.wait_group 0;" ::: "memory");
}
__device__ __forceinline__ void prefetch_tmap(const CUtensorMap* tm) {
  asm volatile("prefetch.tensormap [%0];" :: "l"(tm) : "memory");
}
__device__ __forceinline__ void fence_proxy_async_global() { asm volatile("fence.proxy.async.global;" ::: "memory"); }
__device__ __forceinline__ void fence_proxy_async_smem() { asm volatile("fence.proxy.async.shared::cta;" ::: "memory"); }
__device__ __forceinline__ unsigned ld_relaxed(const unsigned* p) {
  unsigned v;
  asm volatile("ld.relaxed.gpu.global.u32 %0, [%1];" : "=r"(v) : "l"(p) : "memory");
  return v;
}
__device__ __forceinline__ void fence_acquire() { asm volatile("fence.acquire.gpu;" ::: "memory"); }
__device__ __forceinline__ void wait_flag(const unsigned* p, unsigned target) {
  int it = 0;
  while ((int)(ld_relaxed(p) - target) < 0 && ++it < (1 << 20)) {}
  fence_acquire();
}
__device__ __forceinline__ void signal_release(unsigned* p) {
  asm volatile("red.release.gpu.global.add.u32 [%0], 1;" :: "l"(p) : "memory");
}
template <int ID, int N> __device__ __forceinline__ void bar_arrive() { asm volatile("bar.arrive %0, %1;" :: "n"(ID), "n"(N) : "memory"); }
template <int ID, int N> __device__ __forceinline__ void bar_sync() { asm volatile("bar.sync %0, %1;" :: "n"(ID), "n"(N) : "memory"); }
__device__ __forceinline__ void bar_wg(int wg) { asm volatile("bar.sync %0, 128;" :: "r"(2 + wg) : "memory"); }
__device__ __forceinline__ void cluster_sync() {
  asm volatile("barrier.cluster.arrive.relaxed.aligned;\nbarrier.cluster.wait.aligned;" ::: "memory");
}
__device__ __forceinline__ void cluster_wait() { asm volatile("barrier.cluster.wait.acquire.aligned;" ::: "memory"); }
enum { BAR_X1 = 7, BAR_WF = 8  , BAR_SKEW = 10 };

__device__ __forceinline__ void wgmma_fence() { asm volatile("wgmma.fence.sync.aligned;" ::: "memory"); }
__device__ __forceinline__ void wgmma_commit() { asm volatile("wgmma.commit_group.sync.aligned;" ::: "memory"); }
template <int N> __device__ __forceinline__ void wgmma_wait() { asm volatile("wgmma.wait_group.sync.aligned %0;" :: "n"(N) : "memory"); }

template <int scale_d, int tnsp_b = 1> __device__ __forceinline__ void wgmma_n192(float* d, uint64_t descA, uint64_t descB) {
  asm volatile("{\n.reg .pred p;\nsetp.ne.b32 p, %98, 0;\n"
               "wgmma.mma_async.sync.aligned.m64n192k16.f32.bf16.bf16 {%0,%1,%2,%3,%4,%5,%6,%7,%8,%9,%10,%11,%12,%13,%14,%15,%16,%17,%18,%19,%20,%21,%22,%23,%24,%25,%26,%27,%28,%29,%30,%31,%32,%33,%34,%35,%36,%37,%38,%39,%40,%41,%42,%43,%44,%45,%46,%47,%48,%49,%50,%51,%52,%53,%54,%55,%56,%57,%58,%59,%60,%61,%62,%63,%64,%65,%66,%67,%68,%69,%70,%71,%72,%73,%74,%75,%76,%77,%78,%79,%80,%81,%82,%83,%84,%85,%86,%87,%88,%89,%90,%91,%92,%93,%94,%95}, %96, %97, p, 1, 1, 0, %99;\n}\n"
               : "+f"(d[0]), "+f"(d[1]), "+f"(d[2]), "+f"(d[3]), "+f"(d[4]), "+f"(d[5]), "+f"(d[6]), "+f"(d[7]), "+f"(d[8]), "+f"(d[9]), "+f"(d[10]), "+f"(d[11]), "+f"(d[12]), "+f"(d[13]), "+f"(d[14]), "+f"(d[15]), "+f"(d[16]), "+f"(d[17]), "+f"(d[18]), "+f"(d[19]), "+f"(d[20]), "+f"(d[21]), "+f"(d[22]), "+f"(d[23]), "+f"(d[24]), "+f"(d[25]), "+f"(d[26]), "+f"(d[27]), "+f"(d[28]), "+f"(d[29]), "+f"(d[30]), "+f"(d[31]), "+f"(d[32]), "+f"(d[33]), "+f"(d[34]), "+f"(d[35]), "+f"(d[36]), "+f"(d[37]), "+f"(d[38]), "+f"(d[39]), "+f"(d[40]), "+f"(d[41]), "+f"(d[42]), "+f"(d[43]), "+f"(d[44]), "+f"(d[45]), "+f"(d[46]), "+f"(d[47]), "+f"(d[48]), "+f"(d[49]), "+f"(d[50]), "+f"(d[51]), "+f"(d[52]), "+f"(d[53]), "+f"(d[54]), "+f"(d[55]), "+f"(d[56]), "+f"(d[57]), "+f"(d[58]), "+f"(d[59]), "+f"(d[60]), "+f"(d[61]), "+f"(d[62]), "+f"(d[63]), "+f"(d[64]), "+f"(d[65]), "+f"(d[66]), "+f"(d[67]), "+f"(d[68]), "+f"(d[69]), "+f"(d[70]), "+f"(d[71]), "+f"(d[72]), "+f"(d[73]), "+f"(d[74]), "+f"(d[75]), "+f"(d[76]), "+f"(d[77]), "+f"(d[78]), "+f"(d[79]), "+f"(d[80]), "+f"(d[81]), "+f"(d[82]), "+f"(d[83]), "+f"(d[84]), "+f"(d[85]), "+f"(d[86]), "+f"(d[87]), "+f"(d[88]), "+f"(d[89]), "+f"(d[90]), "+f"(d[91]), "+f"(d[92]), "+f"(d[93]), "+f"(d[94]), "+f"(d[95])
               : "l"(descA), "l"(descB), "n"(scale_d), "n"(tnsp_b));
}
template <int scale_d> __device__ __forceinline__ void wgmma4_n192(float* d, uint32_t da, uint32_t db) {
#define R_ "{%0,%1,%2,%3,%4,%5,%6,%7,%8,%9,%10,%11,%12,%13,%14,%15,%16,%17,%18,%19,%20,%21,%22,%23,%24,%25,%26,%27,%28,%29,%30,%31,%32,%33,%34,%35,%36,%37,%38,%39,%40,%41,%42,%43,%44,%45,%46,%47,%48,%49,%50,%51,%52,%53,%54,%55,%56,%57,%58,%59,%60,%61,%62,%63,%64,%65,%66,%67,%68,%69,%70,%71,%72,%73,%74,%75,%76,%77,%78,%79,%80,%81,%82,%83,%84,%85,%86,%87,%88,%89,%90,%91,%92,%93,%94,%95}"
  asm volatile("{\n.reg .pred p, q;\n.reg .b64 a, b;\nsetp.ne.b32 p, %98, 0;\nsetp.eq.b32 q, 0, 0;\nmov.b64 a, {%96, 0x40000040};\nmov.b64 b, {%97, 0x40000040};\n"
               "wgmma.mma_async.sync.aligned.m64n192k16.f32.bf16.bf16 " R_ ", a, b, p, 1, 1, 0, 1;\nadd.s64 a, a, 2;\nadd.s64 b, b, 128;\n"
               "wgmma.mma_async.sync.aligned.m64n192k16.f32.bf16.bf16 " R_ ", a, b, q, 1, 1, 0, 1;\nadd.s64 a, a, 2;\nadd.s64 b, b, 128;\n"
               "wgmma.mma_async.sync.aligned.m64n192k16.f32.bf16.bf16 " R_ ", a, b, q, 1, 1, 0, 1;\nadd.s64 a, a, 2;\nadd.s64 b, b, 128;\n"
               "wgmma.mma_async.sync.aligned.m64n192k16.f32.bf16.bf16 " R_ ", a, b, q, 1, 1, 0, 1;\n}\n"
               : "+f"(d[0]), "+f"(d[1]), "+f"(d[2]), "+f"(d[3]), "+f"(d[4]), "+f"(d[5]), "+f"(d[6]), "+f"(d[7]), "+f"(d[8]), "+f"(d[9]), "+f"(d[10]), "+f"(d[11]), "+f"(d[12]), "+f"(d[13]), "+f"(d[14]), "+f"(d[15]), "+f"(d[16]), "+f"(d[17]), "+f"(d[18]), "+f"(d[19]), "+f"(d[20]), "+f"(d[21]), "+f"(d[22]), "+f"(d[23]), "+f"(d[24]), "+f"(d[25]), "+f"(d[26]), "+f"(d[27]), "+f"(d[28]), "+f"(d[29]), "+f"(d[30]), "+f"(d[31]), "+f"(d[32]), "+f"(d[33]), "+f"(d[34]), "+f"(d[35]), "+f"(d[36]), "+f"(d[37]), "+f"(d[38]), "+f"(d[39]), "+f"(d[40]), "+f"(d[41]), "+f"(d[42]), "+f"(d[43]), "+f"(d[44]), "+f"(d[45]), "+f"(d[46]), "+f"(d[47]), "+f"(d[48]), "+f"(d[49]), "+f"(d[50]), "+f"(d[51]), "+f"(d[52]), "+f"(d[53]), "+f"(d[54]), "+f"(d[55]), "+f"(d[56]), "+f"(d[57]), "+f"(d[58]), "+f"(d[59]), "+f"(d[60]), "+f"(d[61]), "+f"(d[62]), "+f"(d[63]), "+f"(d[64]), "+f"(d[65]), "+f"(d[66]), "+f"(d[67]), "+f"(d[68]), "+f"(d[69]), "+f"(d[70]), "+f"(d[71]), "+f"(d[72]), "+f"(d[73]), "+f"(d[74]), "+f"(d[75]), "+f"(d[76]), "+f"(d[77]), "+f"(d[78]), "+f"(d[79]), "+f"(d[80]), "+f"(d[81]), "+f"(d[82]), "+f"(d[83]), "+f"(d[84]), "+f"(d[85]), "+f"(d[86]), "+f"(d[87]), "+f"(d[88]), "+f"(d[89]), "+f"(d[90]), "+f"(d[91]), "+f"(d[92]), "+f"(d[93]), "+f"(d[94]), "+f"(d[95])
               : "r"(da), "r"(db), "n"(scale_d));
#undef R_
}
template <int scale_d> __device__ __forceinline__ void wgmma4_n128(float* d, uint32_t da, uint32_t db) {
#define R_ "{%0,%1,%2,%3,%4,%5,%6,%7,%8,%9,%10,%11,%12,%13,%14,%15,%16,%17,%18,%19,%20,%21,%22,%23,%24,%25,%26,%27,%28,%29,%30,%31,%32,%33,%34,%35,%36,%37,%38,%39,%40,%41,%42,%43,%44,%45,%46,%47,%48,%49,%50,%51,%52,%53,%54,%55,%56,%57,%58,%59,%60,%61,%62,%63}"
  asm volatile("{\n.reg .pred p, q;\n.reg .b64 a, b;\nsetp.ne.b32 p, %66, 0;\nsetp.eq.b32 q, 0, 0;\nmov.b64 a, {%64, 0x40000040};\nmov.b64 b, {%65, 0x40000040};\n"
               "wgmma.mma_async.sync.aligned.m64n128k16.f32.bf16.bf16 " R_ ", a, b, p, 1, 1, 0, 1;\nadd.s64 a, a, 2;\nadd.s64 b, b, 128;\n"
               "wgmma.mma_async.sync.aligned.m64n128k16.f32.bf16.bf16 " R_ ", a, b, q, 1, 1, 0, 1;\nadd.s64 a, a, 2;\nadd.s64 b, b, 128;\n"
               "wgmma.mma_async.sync.aligned.m64n128k16.f32.bf16.bf16 " R_ ", a, b, q, 1, 1, 0, 1;\nadd.s64 a, a, 2;\nadd.s64 b, b, 128;\n"
               "wgmma.mma_async.sync.aligned.m64n128k16.f32.bf16.bf16 " R_ ", a, b, q, 1, 1, 0, 1;\n}\n"
               : "+f"(d[0]), "+f"(d[1]), "+f"(d[2]), "+f"(d[3]), "+f"(d[4]), "+f"(d[5]), "+f"(d[6]), "+f"(d[7]), "+f"(d[8]), "+f"(d[9]), "+f"(d[10]), "+f"(d[11]), "+f"(d[12]), "+f"(d[13]), "+f"(d[14]), "+f"(d[15]), "+f"(d[16]), "+f"(d[17]), "+f"(d[18]), "+f"(d[19]), "+f"(d[20]), "+f"(d[21]), "+f"(d[22]), "+f"(d[23]), "+f"(d[24]), "+f"(d[25]), "+f"(d[26]), "+f"(d[27]), "+f"(d[28]), "+f"(d[29]), "+f"(d[30]), "+f"(d[31]), "+f"(d[32]), "+f"(d[33]), "+f"(d[34]), "+f"(d[35]), "+f"(d[36]), "+f"(d[37]), "+f"(d[38]), "+f"(d[39]), "+f"(d[40]), "+f"(d[41]), "+f"(d[42]), "+f"(d[43]), "+f"(d[44]), "+f"(d[45]), "+f"(d[46]), "+f"(d[47]), "+f"(d[48]), "+f"(d[49]), "+f"(d[50]), "+f"(d[51]), "+f"(d[52]), "+f"(d[53]), "+f"(d[54]), "+f"(d[55]), "+f"(d[56]), "+f"(d[57]), "+f"(d[58]), "+f"(d[59]), "+f"(d[60]), "+f"(d[61]), "+f"(d[62]), "+f"(d[63])
               : "r"(da), "r"(db), "n"(scale_d));
#undef R_
}
template <int scale_d> __device__ __forceinline__ void wgmma_n32(float* d, uint64_t descA, uint64_t descB) {
  asm volatile("{\n.reg .pred p;\nsetp.ne.b32 p, %18, 0;\n"
               "wgmma.mma_async.sync.aligned.m64n32k16.f32.bf16.bf16 {%0,%1,%2,%3,%4,%5,%6,%7,%8,%9,%10,%11,%12,%13,%14,%15}, %16, %17, p, 1, 1, 0, 1;\n}\n"
               : "+f"(d[0]), "+f"(d[1]), "+f"(d[2]), "+f"(d[3]), "+f"(d[4]), "+f"(d[5]), "+f"(d[6]), "+f"(d[7]), "+f"(d[8]), "+f"(d[9]), "+f"(d[10]), "+f"(d[11]), "+f"(d[12]), "+f"(d[13]), "+f"(d[14]), "+f"(d[15])
               : "l"(descA), "l"(descB), "n"(scale_d));
}
template <int scale_d, int tnsp_a> __device__ __forceinline__ void wgmma_n40(float* d, uint64_t descA, uint64_t descB) {
  asm volatile("{\n.reg .pred p;\nsetp.ne.b32 p, %22, 0;\n"
               "wgmma.mma_async.sync.aligned.m64n40k16.f32.bf16.bf16 {%0,%1,%2,%3,%4,%5,%6,%7,%8,%9,%10,%11,%12,%13,%14,%15,%16,%17,%18,%19}, %20, %21, p, 1, 1, %23, 1;\n}\n"
               : "+f"(d[0]), "+f"(d[1]), "+f"(d[2]), "+f"(d[3]), "+f"(d[4]), "+f"(d[5]), "+f"(d[6]), "+f"(d[7]), "+f"(d[8]), "+f"(d[9]), "+f"(d[10]), "+f"(d[11]), "+f"(d[12]), "+f"(d[13]), "+f"(d[14]), "+f"(d[15]), "+f"(d[16]), "+f"(d[17]), "+f"(d[18]), "+f"(d[19])
               : "l"(descA), "l"(descB), "n"(scale_d), "n"(tnsp_a));
}
template <int scale_d> __device__ __forceinline__ void wgmma_n40_rs(float* d, const uint32_t* a, uint64_t descB) {
  asm volatile("{\n.reg .pred p;\nsetp.ne.b32 p, %25, 0;\n"
               "wgmma.mma_async.sync.aligned.m64n40k16.f32.bf16.bf16 {%0,%1,%2,%3,%4,%5,%6,%7,%8,%9,%10,%11,%12,%13,%14,%15,%16,%17,%18,%19}, {%20,%21,%22,%23}, %24, p, 1, 1, 1;\n}\n"
               : "+f"(d[0]), "+f"(d[1]), "+f"(d[2]), "+f"(d[3]), "+f"(d[4]), "+f"(d[5]), "+f"(d[6]), "+f"(d[7]), "+f"(d[8]), "+f"(d[9]), "+f"(d[10]), "+f"(d[11]), "+f"(d[12]), "+f"(d[13]), "+f"(d[14]), "+f"(d[15]), "+f"(d[16]), "+f"(d[17]), "+f"(d[18]), "+f"(d[19])
               : "r"(a[0]), "r"(a[1]), "r"(a[2]), "r"(a[3]), "l"(descB), "n"(scale_d));
}
__device__ __forceinline__ uint64_t make_desc(uint32_t addr, uint32_t lbo_bytes, uint32_t sbo_bytes) {
  return (uint64_t)((addr & 0x3FFFF) >> 4) | ((uint64_t)(lbo_bytes >> 4) << 16) | ((uint64_t)(sbo_bytes >> 4) << 32) | (1ull << 62);
}

__device__ __forceinline__ void ldsm_x4(uint32_t addr, uint32_t& r0, uint32_t& r1, uint32_t& r2, uint32_t& r3) {
  asm volatile("ldmatrix.sync.aligned.m8n8.x4.shared.b16 {%0,%1,%2,%3}, [%4];" : "=r"(r0), "=r"(r1), "=r"(r2), "=r"(r3) : "r"(addr) : "memory");
}
__device__ __forceinline__ void ldsm_x4_t(uint32_t addr, uint32_t& r0, uint32_t& r1, uint32_t& r2, uint32_t& r3) {
  asm volatile("ldmatrix.sync.aligned.m8n8.x4.trans.shared.b16 {%0,%1,%2,%3}, [%4];" : "=r"(r0), "=r"(r1), "=r"(r2), "=r"(r3) : "r"(addr) : "memory");
}
__device__ __forceinline__ void stsm_x4(uint32_t addr, uint32_t r0, uint32_t r1, uint32_t r2, uint32_t r3) {
  asm volatile("stmatrix.sync.aligned.m8n8.x4.shared.b16 [%0], {%1,%2,%3,%4};" :: "r"(addr), "r"(r0), "r"(r1), "r"(r2), "r"(r3) : "memory");
}
__device__ __forceinline__ void sts128(uint32_t addr, uint32_t a, uint32_t b, uint32_t c, uint32_t d) {
  asm volatile("st.shared.v4.u32 [%0], {%1,%2,%3,%4};" :: "r"(addr), "r"(a), "r"(b), "r"(c), "r"(d) : "memory");
}
__device__ __forceinline__ float lds32f(uint32_t addr) {
  float v;
  asm volatile("ld.shared.f32 %0, [%1];" : "=f"(v) : "r"(addr) : "memory");
  return v;
}
__device__ __forceinline__ void sts32f(uint32_t addr, float a) {
  asm volatile("st.shared.f32 [%0], %1;" :: "r"(addr), "f"(a) : "memory");
}
__device__ __forceinline__ void mma_bf16(float (&c)[4], uint32_t a0, uint32_t a1, uint32_t a2, uint32_t a3, uint32_t b0, uint32_t b1) {
  asm volatile("mma.sync.aligned.m16n8k16.row.col.f32.bf16.bf16.f32 {%0,%1,%2,%3}, {%4,%5,%6,%7}, {%8,%9}, {%0,%1,%2,%3};"
               : "+f"(c[0]), "+f"(c[1]), "+f"(c[2]), "+f"(c[3]) : "r"(a0), "r"(a1), "r"(a2), "r"(a3), "r"(b0), "r"(b1));
}
__device__ __forceinline__ void mma_bf16_z(float (&c)[4], uint32_t a0, uint32_t a1, uint32_t a2, uint32_t a3, uint32_t b0, uint32_t b1) {
  asm volatile("mma.sync.aligned.m16n8k16.row.col.f32.bf16.bf16.f32 {%0,%1,%2,%3}, {%4,%5,%6,%7}, {%8,%9}, {%10,%10,%10,%10};"
               : "=f"(c[0]), "=f"(c[1]), "=f"(c[2]), "=f"(c[3]) : "r"(a0), "r"(a1), "r"(a2), "r"(a3), "r"(b0), "r"(b1), "f"(0.f));
}
__device__ __forceinline__ uint32_t movm_t(uint32_t v) {
  uint32_t r;
  asm volatile("movmatrix.sync.aligned.m8n8.trans.b16 %0, %1;" : "=r"(r) : "r"(v));
  return r;
}
__device__ __forceinline__ uint32_t pack_bf16(float lo, float hi) {
  uint32_t r;
  asm("cvt.rn.bf16x2.f32 %0, %1, %2;" : "=r"(r) : "f"(hi), "f"(lo));
  return r;
}
__device__ __forceinline__ float bf_lo(uint32_t v) { return __uint_as_float(v << 16); }
__device__ __forceinline__ float bf_hi(uint32_t v) { return __uint_as_float(v & 0xFFFF0000u); }
__device__ __forceinline__ void split3(float x, uint32_t& h, uint32_t& m, uint32_t& l) {
  h = pack_bf16(x, 0.f); x -= bf_lo(h);
  m = pack_bf16(x, 0.f); x -= bf_lo(m);
  l = pack_bf16(x, 0.f);
}
__device__ __forceinline__ float ex2(float x) { float r; asm("ex2.approx.ftz.f32 %0, %1;" : "=f"(r) : "f"(x)); return r; }
__device__ __forceinline__ float rcp_fast(float x) { float r; asm("rcp.approx.ftz.f32 %0, %1;" : "=f"(r) : "f"(x)); return r; }
__device__ __forceinline__ void red_v4(float* p, float a, float b, float c, float d) {
  asm volatile("red.global.add.v4.f32 [%0], {%1, %2, %3, %4};" :: "l"(p), "f"(a), "f"(b), "f"(c), "f"(d) : "memory");
}
__device__ __forceinline__ uint4 ld_ll(const uint4* p) {
  uint4 v;
  asm volatile("{\n.reg .b64 a, b;\nld.relaxed.gpu.global.v2.b64 {a, b}, [%4];\nmov.b64 {%0, %1}, a;\nmov.b64 {%2, %3}, b;\n}\n"
               : "=r"(v.x), "=r"(v.y), "=r"(v.z), "=r"(v.w) : "l"(p) : "memory");
  return v;
}
__device__ __forceinline__ void st_b64(uint2* p, uint32_t a, uint32_t b) {
  asm volatile("{\n.reg .b64 v;\nmov.b64 v, {%1, %2};\nst.relaxed.gpu.global.b64 [%0], v;\n}\n" :: "l"(p), "r"(a), "r"(b) : "memory");
}
__device__ __forceinline__ void st_b128(uint4* p, uint32_t a, uint32_t b, uint32_t c, uint32_t d) {
  asm volatile("{\n.reg .b128 v;\nmov.b128 v, {%1, %2, %3, %4};\nst.relaxed.gpu.global.b128 [%0], v;\n}\n" :: "l"(p), "r"(a), "r"(b), "r"(c), "r"(d) : "memory");
}
__device__ __forceinline__ uint4 ld_b128(const uint4* p) {
  uint4 v;
  asm volatile("{\n.reg .b128 v;\nld.relaxed.gpu.global.b128 v, [%4];\nmov.b128 {%0, %1, %2, %3}, v;\n}\n" : "=r"(v.x), "=r"(v.y), "=r"(v.z), "=r"(v.w) : "l"(p) : "memory");
  return v;
}

constexpr float LOG2E = 1.4426950408889634f;

struct Params {
  const __nv_bfloat16* x0;
  const __nv_bfloat16* wA_qkv;
  const __nv_bfloat16* wA_o;
  const __nv_bfloat16* wB_qkv;
  const __nv_bfloat16* wB_phi;
  const __nv_bfloat16* wB_o;
  __nv_bfloat16* out;
};

#define ACC_DEF(d, n) _Pragma("unroll") for (int i_ = 0; i_ < (n); i_++) asm volatile("" : "=f"(d[i_]))
#define ACC_FENCE(d, n) _Pragma("unroll") for (int i_ = 0; i_ < (n); i_++) asm volatile("" : "+f"(d[i_]) :: "memory")
#define PIN(a, n) _Pragma("unroll") for (int i_ = 0; i_ < (n); i_++) asm volatile("" : "+f"((a)[i_]))
#define PINU(a, n) _Pragma("unroll") for (int i_ = 0; i_ < (n); i_++) asm volatile("" : "+r"((a)[i_]))

#define STAGE_V(acc, p0) { \
    _Pragma("unroll") for (int j_ = 0; j_ < 4; j_++) { \
      const float* a_ = (acc) + j_ * 8; \
      stsm_x4((p0) + (j_ >> 1) * 8192 + (srowoff >> 1) + ((((uint32_t)(j_ & 1) << 5) + lhi) ^ lsw2), \
              pack_bf16(rs0 * a_[0], rs0 * a_[1]), pack_bf16(rs1 * a_[2], rs1 * a_[3]), pack_bf16(rs0 * a_[4], rs0 * a_[5]), pack_bf16(rs1 * a_[6], rs1 * a_[7])); } }
#define FRAG(dst, acc, TR, grp) { \
    _Pragma("unroll") for (int i_ = 0; i_ < 16; i_++) { \
      const float r_ = (i_ & 1) ? rs1 : rs0; \
      const uint32_t w_ = pack_bf16(r_ * (acc)[2 * i_], r_ * (acc)[2 * i_ + 1]); \
      if (TR) (dst)[i_] = movm_t(w_); else (dst)[(i_ & 12) + (i_ & 1) * 2 + ((i_ >> 1) & 1)] = w_; } \
    if (warp == 7 && mm < 15) { \
      _Pragma("unroll") for (int j_ = 0; j_ < 4; j_++) \
        st_b128(g_halo + (size_t)(mm * 8 + jj) * 512 + ((grp) * 4 + j_) * 32 + lane, ((dst)[j_ * 4] & ~1u) | H_BIT(l), (dst)[j_ * 4 + 1], (dst)[j_ * 4 + 2], (dst)[j_ * 4 + 3]); } \
    PINU(dst, 16); }
#define FRAG_PUT(src, slot) if (warp < 7) { _Pragma("unroll") for (int j_ = 0; j_ < 4; j_++) \
      sts128(sbase + (slot) * SLOT + 2048 + warp * 2048 + j_ * 512 + lane * 16, (src)[j_ * 4], (src)[j_ * 4 + 1], (src)[j_ * 4 + 2], (src)[j_ * 4 + 3]); }
#define FRAG_GET(dst, slot) { _Pragma("unroll") for (int j_ = 0; j_ < 4; j_++) \
      asm volatile("ld.shared.v4.u32 {%0, %1, %2, %3}, [%4];" : "=r"((dst)[j_ * 4]), "=r"((dst)[j_ * 4 + 1]), "=r"((dst)[j_ * 4 + 2]), "=r"((dst)[j_ * 4 + 3]) \
                   : "r"(sbase + (slot) * SLOT + warp * 2048 + j_ * 512 + lane * 16) : "memory"); }
#define RW(j) (((j) >> 1) * 4 + ((j) & 1))
__device__ __forceinline__ float rmax16(const float* p) {
  float m[4];
#pragma unroll
  for (int j = 0; j < 4; j++) m[j] = fmaxf(fmaxf(p[RW(j)], p[RW(j + 4)]), fmaxf(p[RW(j + 8)], p[RW(j + 12)]));
  const float r = fmaxf(fmaxf(m[0], m[1]), fmaxf(m[2], m[3]));
  return fmaxf(r, __shfl_xor_sync(0xffffffffu, r, 1));
}
__device__ __forceinline__ float rmin16(const float* p) {
  float m[4];
#pragma unroll
  for (int j = 0; j < 4; j++) m[j] = fminf(fminf(p[RW(j)], p[RW(j + 4)]), fminf(p[RW(j + 8)], p[RW(j + 12)]));
  const float r = fminf(fminf(m[0], m[1]), fminf(m[2], m[3]));
  return fminf(r, __shfl_xor_sync(0xffffffffu, r, 1));
}
__device__ __forceinline__ float exps16(float* o, const float* p, float c, float b) {
  float s[4];
#pragma unroll
  for (int j = 0; j < 16; j++) { o[j] = ex2(fmaf(p[RW(j)], c, b)); if (j < 4) s[j] = o[j]; else s[j & 3] += o[j]; }
  return (s[0] + s[1]) + (s[2] + s[3]);
}
__device__ __forceinline__ void store16(const float* e, float sum, uint32_t dst, uint32_t dsw, int c0) {
  const float inv = rcp_fast(sum + __shfl_xor_sync(0xffffffffu, sum, 1));
#pragma unroll
  for (int j = 0; j < 2; j++)
    sts128(dst + (((c0 + j) << 4) ^ dsw), pack_bf16(e[j * 8] * inv, e[j * 8 + 1] * inv), pack_bf16(e[j * 8 + 2] * inv, e[j * 8 + 3] * inv),
           pack_bf16(e[j * 8 + 4] * inv, e[j * 8 + 5] * inv), pack_bf16(e[j * 8 + 6] * inv, e[j * 8 + 7] * inv));
}
__device__ __forceinline__ void expp16(uint32_t* o, const float* p, float c0, float b0, float c1, float b1) {
#pragma unroll
  for (int j = 0; j < 8; j++) {
    const float c = (j & 1) ? c1 : c0, b = (j & 1) ? b1 : b0;
    o[j] = pack_bf16(ex2(fmaf(p[2 * j], c, b)), ex2(fmaf(p[2 * j + 1], c, b)));
  }
}
__device__ __forceinline__ void extrema(float* m, const float* p, float c0, float c1) {
#pragma unroll
  for (int i = 0; i < 4; i++) {
    const float* q = p + (i >> 1) * 16 + (i & 1) * 2;
    m[(i >> 1) * 4 + (i & 1)] = fminf(fminf(fminf(q[0], q[1]), fminf(q[4], q[5])), fminf(fminf(q[8], q[9]), fminf(q[12], q[13])));
    m[(i >> 1) * 4 + (i & 1) + 2] = fmaxf(fmaxf(fmaxf(q[0], q[1]), fmaxf(q[4], q[5])), fmaxf(fmaxf(q[8], q[9]), fmaxf(q[12], q[13])));
  }
#pragma unroll
  for (int o = 1; o <= 2; o <<= 1)
#pragma unroll
    for (int i = 0; i < 8; i++) { const float x = __shfl_xor_sync(0xffffffffu, m[i], o); m[i] = (i & 2) ? fmaxf(m[i], x) : fminf(m[i], x); }
#pragma unroll
  for (int i = 0; i < 8; i++) m[i] *= ((i & 2) ? -1.f : 1.f) * ((i & 1) ? c1 : c0);
}
#define SCHED_FENCE() asm volatile("pmevent 0;" ::: "memory")

__global__ void __cluster_dims__(2, 1, 1) __launch_bounds__(384, 1)
mega_kernel(const __grid_constant__ CUtensorMap tm_x0, const __grid_constant__ CUtensorMap tm_xo, const __grid_constant__ CUtensorMap tm_os,
            const __grid_constant__ CUtensorMap tm_o, const __grid_constant__ CUtensorMap tm_wf,
            const __grid_constant__ CUtensorMap tm_wqA, const __grid_constant__ CUtensorMap tm_wqB,
            const __grid_constant__ CUtensorMap tm_woA, const __grid_constant__ CUtensorMap tm_woB,
            const __grid_constant__ CUtensorMap tm_phi, const Params prm) {
  extern __shared__ __align__(1024) uint8_t smem_raw[];
  const uint32_t sbase = smem_u32(smem_raw);
  const uint32_t bar_full = sbase + OFF_BAR;
  const uint32_t bar_done = bar_full + 384;
  const uint32_t bar_stat = bar_full + 768, bar_stat2 = bar_full + 776, bar_epi = bar_full + 784, bar_phi = bar_full + 936  , bar_halo = bar_full + 904  ;
  const uint32_t bar_xr = bar_full + 800, bar_lx = bar_full + 808, bar_stg = bar_full + 832;
  const uint32_t bar_chk = bar_full + 848;

  const int warp = __shfl_sync(0xffffffffu, threadIdx.x >> 5, 0), lane = threadIdx.x & 31;
  uint32_t rank;
  asm volatile("mov.u32 %0, %%cluster_ctarank;" : "=r"(rank));
  const int aux = (int)blockIdx.x - NMAIN, tp = (int)(blockIdx.x >> 1) - 4;
  const int gp = tp < 0 ? 0 : (tp < 32 ? tp & 7 : 1 + (tp - 32) % 7), me = tp < 0 ? tp + 8 : (tp < 32 ? tp >> 3 : 4 + (tp - 32) / 7);
  const int jj = me, cc = gp;
  const int cta = aux >= 0 ? -1 : (cc * 8 + jj) * 2 + (int)rank;
  const int mm = cc * 2 + (int)rank;

#define LOAD_EPOCH() const unsigned epoch = ld_relaxed(&g_flags.epoch.v), ep1 = epoch + 1; (void)epoch
  int budget = 1 << 22;

  if (cta >= 0) {
    {
      const int tx = threadIdx.x;
      const __nv_bfloat16* pf = (tx < 128) ? prm.x0 + (size_t)(mm * 128 + tx) * D_MODEL + jj * 128
                                           : prm.wA_qkv + (size_t)(jj * 128 + (tx & 63)) * 3072 + ((tx - 128) >> 6) * 1024 + jj * 128 + rank * 64;
      if (tx < 320) asm volatile("prefetch.global.L2 [%0];" :: "l"(pf));
      else if (tx == 320) prefetch_tmap(&tm_x0);
      else if (tx == 352) prefetch_tmap(&tm_wqA);
      else if (tx == 383) asm volatile("prefetch.global.L2 [%0];" :: "l"(&g_flags.epoch.v));
    }
    if (elect_one()) {
#pragma unroll
      for (int i = 0; i < 4; i++) {
        const int u = warp * 4 + i;
        mbar_init(bar_full + u * 8, ((u >= 4 && u < 11) || (u > 32 && u != 40)) ? 2 : 1); mbar_init(bar_done + u * 8, 16);
      }
      mbar_init(bar_stat + warp * 16, 0x111111181182ull >> (4 * warp) & 15);
      mbar_init(bar_stat + warp * 16 + 8, 0x111111121811ull >> (4 * warp) & 15);
      mbar_init(bar_chk + 112 + (warp & 7) * 8, 1);
      asm volatile("fence.mbarrier_init.release.cluster;" ::: "memory");
    }
    __syncthreads();
    asm volatile("barrier.cluster.arrive.relaxed.aligned;" ::: "memory");
  }

  if (cta < 0) {
    LOAD_EPOCH();
    const uint32_t buf = sbase + warp * SLOT, bar = sbase + OFF_BAR + warp * 16;
    const uint32_t lsw = (lane & 7) << 4, lhi = (lane >> 4) << 4, lrow = (lane & 15) * 128;
    const bool el = elect_one();
    if (el) {
      mbar_init(bar, 1); mbar_init(bar + 8, 1);
      asm volatile("fence.mbarrier_init.release.cluster;" ::: "memory");
    }
#pragma unroll 1
    for (int rd = 0; rd < (NLAYERS > 1 ? 5 : 2); rd++) {
      if (rd >= 2 && warp >= 8) break;
      const int tk = rd < 2 ? aux * 12 + warp : aux * 8 + warp;
      const int half = tk & 1;
      const int blk = rd < 2 ? (tk >> 1) * 2 + rd : (4 - rd) * 16 + (tk >> 1);
      const CUtensorMap* tm = rd < 2 ? &tm_wqA : (rd == 2 ? &tm_wqB : &tm_wf);
      const int j0 = (blk & 15) >> 1;
#define AUX_LOAD(n) { const uint32_t d_ = buf + ((n) & 1) * 8192, b_ = bar + ((n) & 1) * 8; const int r_ = kslice(j0, 2 * (n) + half) * 64; \
        mbar_expect_tx(b_, 8192); tma_load_2d(d_, tm, b_, blk * 64, r_); tma_load_2d(d_ + 4096, tm, b_, blk * 64, r_ + 32); }
      if (el) {
        if (rd == 3) { wait_flag(&g_flags.wfready[j0].v, ep1 * 16); fence_proxy_async_global(); }
        AUX_LOAD(0); AUX_LOAD(1);
      }
      __syncwarp();
      float cs[8][4];
#pragma unroll
      for (int i = 0; i < 8; i++) cs[i][0] = cs[i][1] = cs[i][2] = cs[i][3] = 0.f;
#pragma unroll 1
      for (int n = 0; n < 8; n++) {
        const uint32_t tb = buf + (n & 1) * 8192 + lrow;
        mbar_wait(bar + (n & 1) * 8, (n >> 1) & 1);
#pragma unroll
        for (int i = 0; i < 16; i++) {
          uint32_t b0, b1, b2, b3;
          ldsm_x4_t(tb + (i >> 2) * 2048 + (((i & 3) * 32 + lhi) ^ lsw), b0, b1, b2, b3);
          mma_bf16(cs[2 * (i & 3)], 0x3F803F80u, 0x3F803F80u, 0x3F803F80u, 0x3F803F80u, b0, b1);
          mma_bf16(cs[2 * (i & 3) + 1], 0x3F803F80u, 0x3F803F80u, 0x3F803F80u, 0x3F803F80u, b2, b3);
        }
        __syncwarp();
        if (el && n < 6) AUX_LOAD(n + 2);
        __syncwarp();
      }
      if (lane < 4) {
#pragma unroll
        for (int i = 0; i < 8; i++) st_b64(&g_colsum[rd >= 2][blk * 32 + i * 4 + lane][half], __float_as_uint(cs[i][0]), (__float_as_uint(cs[i][1]) & ~3u) | (ep1 & 3));
      }
      __syncwarp();
    }
  } else if (warp >= 8) {
    asm volatile("setmaxnreg.dec.sync.aligned.u32 40;");
    if (warp == 8) {
      const bool el = elect_one();
      cluster_wait();
      if (el) {
#pragma unroll 1
        for (int l = 0; l < NLAYERS; l++) {
          const uint32_t par = l & 1;
          const CUtensorMap* tqk = par ? &tm_wf : &tm_wqA;
          const CUtensorMap* tv = par ? &tm_wqB : &tm_wqA;
          const CUtensorMap* two = par ? &tm_woB : &tm_woA;
          if (l == 1) { LOAD_EPOCH(); wait_flag(&g_flags.wfready[jj].v, ep1 * 16); fence_proxy_async_global(); }
#pragma unroll 1
          for (int u = 0; u < 32; u++) {
            if (u >= 4) mbar_wait_sl(bar_done + (u - 4) * 8, par);
            else if (l) mbar_wait_sl(bar_done + (43 + u + (u >> 1)) * 8, par ^ 1);
            else if (u == 1) __nanosleep(STAG1);
            else if (u == 2) mbar_wait_sl(bar_full, 0);
            const uint32_t fb = bar_full + u * 8;
            const bool res = u < 4 ? (l || u >= 2) : (u < 11 || (u >= 18 && u < 22));
            mbar_expect_tx(fb, res ? QST : QST + SLOT);
            const int row = kslice(jj, u < 4 ? u & 1 : (u < 18 ? u - 2 : (u < 22 ? u - 6 : u - 20))) * 64 + (int)rank * 32;
            const int ps = u < 4 ? u >> 1 : (u >= 18), col = jj * 128 + ps * 64;
            const int c0 = par ? jj * 128 + (ps ? 0 : 1024) : col;
            const uint32_t dst = sbase + (u & 3) * QST + rank * 4096;
            tma_load_2d_mc(dst, tqk, fb, c0, row);
            tma_load_2d_mc(dst + 8192, tqk, fb, c0 + (par ? 64 : 1024), row);
            tma_load_2d_mc(dst + 16384, tv, fb, col + 2048, row);
            if (l == PRL && u >= PRU && u < PRU + 4) PROFT(473 + u - PRU);
          }
#pragma unroll 1
          for (int s = 0; s < 16; s++) {
            if (s < 5) { if (s != 2 && s != 4) mbar_wait_sl(bar_done + (28 + s) * 8, par); }
            else if (s != 14) mbar_wait_sl(bar_done + (27 + s - (s == 15)) * 8, par);
            const uint32_t fb = bar_full + (32 + s) * 8;
            mbar_expect_tx(fb, SLOT);
            tma_load_2d_mc(sbase + rank * 8192 + (uint32_t)((WO_BSLOT >> (4 * s)) & 15) * SLOT, two, fb, jj * 128 + (int)rank * 64, wslice(jj, s) * 64);
            const int ts = s + par;
            if (s >= 5 && ts < 8) {
              mbar_expect_tx(bar_chk - 8 + ts * 8, SLOT);
              tma_load_2d(sbase + (uint32_t)((WO_ASLOT(par) >> (4 * ts)) & 15) * SLOT, &tm_o, bar_chk - 8 + ts * 8, wslice(jj, ts) * 64, mm * 128);
            }
          }
        }
      }
      __syncwarp();
    } else if (warp == 9) {
      const bool el = elect_one();
      if (el) {
        PROFT(472);
        tma_load_2d(sbase + OFF_S, &tm_x0, bar_full, jj * 128, mm * 128);
        __nanosleep(STAG1);
        tma_load_2d(sbase + OFF_S + SLOT, &tm_x0, bar_full + 8, jj * 128 + 64, mm * 128);
      }
      __syncwarp();
      LOAD_EPOCH();
#pragma unroll 1
      for (int lp = 0; lp < 4 * NLAYERS; lp++) {
        const int l = lp >> 2, ph = lp & 3;
        if (ph == 3) continue;
        const uint32_t par = l & 1;
        const __nv_bfloat16* pb = g_obuf + (ph >> 1) * 64 + (size_t)(mm * 128 + (ph ? 0 : S_LEN) + (lane & 7) * 16 + (jj & 1) * 8) * D_MODEL + (jj >> 1) * 16;
        const CUtensorMap* tm = lp ? &tm_o : &tm_x0;
        const int row = mm * 128 + ((ph || !l) ? 0 : S_LEN);
        const uint32_t bit = ph ? O_BIT(l) : X_BIT(l - 1);
        const uint32_t slots = ph ? (uint32_t)(WO_ASLOT(par) >> (ph * 32 - 28)) : 0x8769876u;
        const unsigned long long fr = ph == 0 ? XPACE : ph == 1 ? (par ? 0x353535351Full : 0x35351F1Eull) : (par ? 0x27262524232232ull : 0x27262524233232ull);
        uint32_t rdy = (lp == 0 || (lp & 7) == 1) ? 0xFF : 0;
        mbar_wait_sl(ph ? bar_done + ((uint32_t)fr & 63) * 8 : (l ? bar_done + 47 * 8 : bar_full), ph ? par : (l ? par ^ 1 : 0));
#pragma unroll 1
        for (int i = 0; i < (ph == 1 ? 4 + par : 7); i++) {
          if (!((rdy >> i) & 1) && (i < NPOLL || ph == 1)) {
            const unsigned* pp = reinterpret_cast<const unsigned*>(pb + srcb(jj, i + ((lane >> 3) & (POLLW - 1))) * 128);
            if (i == 0) __nanosleep(POLL0);
            unsigned v0 = ld_relaxed(pp);
            __nanosleep(POLLGAP);
            unsigned v1 = ld_relaxed(pp);
            uint32_t no;
#pragma unroll 1
            for (int it = 0; it < (1 << 18); it++) {
              no = __ballot_sync(0xffffffffu, (v0 ^ bit) & 1);
              if (!(no & 0xFF)) break;
              v0 = ld_relaxed(pp);
              no = __ballot_sync(0xffffffffu, (v1 ^ bit) & 1);
              if (!(no & 0xFF)) break;
              v1 = ld_relaxed(pp);
            }
            rdy = ((1 | (no & 0xFF00 ? 0 : 2) | (no & 0xFF0000 ? 0 : 4) | (no >> 24 ? 0 : 8)) & ((1 << POLLW) - 1)) << i;
          }
          if (ph || i >= XP0) mbar_wait_sl(bar_done + ((uint32_t)(fr >> (8 * i)) & 63) * 8, par);
          if (el) {
            if (i == 0) PROFT(320 + l * 16 + ph);
            const uint32_t cb = bar_chk + (ph >> 1) * 112 + i * 8;
            mbar_expect_tx(cb, SLOT);
            tma_load_2d(sbase + ((slots >> (4 * i)) & 15) * SLOT, tm, cb, srcb(jj, i) * 128 + (ph >> 1) * 64, row);
          }
          __syncwarp();
        }
        if (ph == 0 && el) {
          if (l) { wait_flag(&g_flags.xready[l][mm].v, ep1 * 8); fence_proxy_async_global(); }
#pragma unroll 1
          for (int u = 11; u < 34; u++) {
            if (u == 18) u = 22;
            mbar_wait_sl(bar_done + (u - 4) * 8, par);
            if (u == 32) mbar_expect_tx(bar_xr, 2 * SLOT);
            tma_load_2d(sbase + OFF_RA + (u & 3) * SLOT, tm, u < 32 ? bar_full + u * 8 : bar_xr, kslice(jj, u < 18 ? u - 2 : (u < 32 ? u - 20 : u - 32)) * 64, row);
          }
        }
        __syncwarp();
      }
      cluster_wait();
    } else {
      const int hw = warp - 10;
      LOAD_EPOCH();
      const bool el = elect_one();
      cluster_wait();
      if (hw == 0) {
        mbar_wait_sl(bar_full + 8, 0);
        if (lane < 7) prefetch_tmap(lane == 0 ? &tm_os : lane == 1 ? &tm_o : lane == 2 ? &tm_wf : lane == 3 ? &tm_wqB : lane == 4 ? &tm_woA : lane == 5 ? &tm_woB : &tm_phi);
#pragma unroll 1
        for (int i = 0; i < (NLAYERS > 1 ? 9 : 0); i++) {
          if (i == 0 || i == 5) mbar_wait_sl(bar_done + (i >> 1) * 12, 0);
          if (el) {
            if (i == 0) { mbar_expect_tx(bar_phi, 2 * SLOT + 8192); tma_load_2d(sbase + OFF_PHI, &tm_phi, bar_phi, 0, jj * 128); }
            else tma_load_2d(sbase + (i > 4 ? 10 : 12) * SLOT - 4096 + i * 4096, &tm_wqB, bar_phi, (i > 4 ? 896 : 0) + jj * 128 + ((i - 1) >> 1) * 64, mm * 64 + (~i & 1) * 32);
          }
          __syncwarp();
          __nanosleep(PFGAP);
        }
      } else {
#pragma unroll 1
        for (int b = 0; b < 2; b++) {
          float4* z = reinterpret_cast<float4*>(g_kv[b] + (jj * 4) * KVH + mm * (4 * KVH / 16)) + lane;
#pragma unroll
          for (int i = 0; i < 6; i++) z[i * 32] = make_float4(0.f, 0.f, 0.f, 0.f);
        }
#pragma unroll 1
        for (int i = 0; i < 16; i++) {
          const int b = i >> 2;
          const uint32_t v = (b == 0 ? O_BIT(0) : b == 1 ? X_BIT(0) : H_BIT(0)) + 1;
          uint4* p = b < 2 ? reinterpret_cast<uint4*>(g_obuf + (size_t)(b * S_LEN + mm * 128 + (i & 3) * 32 + (lane >> 3) * 8) * D_MODEL + jj * 128 + (b ? 0 : 64)) + (lane & 7)
                           : g_halo + (size_t)(mm * 8 + jj) * 512 + i * 32 + lane;
          *p = make_uint4(v, v, v, v);
        }
        fence_proxy_async_global();
      }
      __syncwarp();
      uint32_t chkp = 0;
#pragma unroll 1
      for (int lp = 0; lp < 4 * NLAYERS; lp++) {
        const int l = lp >> 2, ph = (lp & 3) == 2 ? 2 - hw : (lp & 3);
        const uint32_t par = l & 1;
        int lane; asm volatile("mov.u32 %0, %%laneid;" : "=r"(lane));
        if ((lp & 3) == 2 || (hw && ph == 0)) {
          const uint32_t bit = ph ? O_BIT(l) : X_BIT(l - 1);
          uint32_t slots = ph ? (uint32_t)(WO_ASLOT(par) >> (ph * 32 - 28)) : 0x8769876u;
          const uint32_t a0 = sbase + (lane & 7) * 132 + (lane >> 3) * 32;
#pragma unroll 1
          for (int c = 0; c < 7; c++, slots >>= 4) {
            const uint32_t cb = bar_chk + 112 - hw * 112 + c * 8;
#pragma unroll 1
            for (int it = 0; it < (1 << 12); it++) {
              mbar_wait_sl(cb, (chkp >> c) & 1);
              chkp ^= 1u << c;
              if (el && c == 0) PROFT(ph == 1 ? 480 + l * 2 : 488 + l * 2 + (ph >> 1));
              if (lp == 0) break;
              uint32_t bad;
              asm volatile("{\n.reg .b32 w<16>;\n"
                           "ld.shared.u32 w0, [%1 + 0];\n"
                           "ld.shared.u32 w1, [%1 + 1024];\n"
                           "ld.shared.u32 w2, [%1 + 2048];\n"
                           "ld.shared.u32 w3, [%1 + 3072];\n"
                           "ld.shared.u32 w4, [%1 + 4096];\n"
                           "ld.shared.u32 w5, [%1 + 5120];\n"
                           "ld.shared.u32 w6, [%1 + 6144];\n"
                           "ld.shared.u32 w7, [%1 + 7168];\n"
                           "ld.shared.u32 w8, [%1 + 8192];\n"
                           "ld.shared.u32 w9, [%1 + 9216];\n"
                           "ld.shared.u32 w10, [%1 + 10240];\n"
                           "ld.shared.u32 w11, [%1 + 11264];\n"
                           "ld.shared.u32 w12, [%1 + 12288];\n"
                           "ld.shared.u32 w13, [%1 + 13312];\n"
                           "ld.shared.u32 w14, [%1 + 14336];\n"
                           "ld.shared.u32 w15, [%1 + 15360];\n"
                           "lop3.b32 w0, w0, w1, %2, 0x7E;\n"
                           "lop3.b32 w2, w2, w3, %2, 0x7E;\n"
                           "lop3.b32 w4, w4, w5, %2, 0x7E;\n"
                           "lop3.b32 w6, w6, w7, %2, 0x7E;\n"
                           "lop3.b32 w8, w8, w9, %2, 0x7E;\n"
                           "lop3.b32 w10, w10, w11, %2, 0x7E;\n"
                           "lop3.b32 w12, w12, w13, %2, 0x7E;\n"
                           "lop3.b32 w14, w14, w15, %2, 0x7E;\n"
                           "lop3.b32 w0, w0, w2, w4, 0xFE;\nlop3.b32 w6, w6, w8, w10, 0xFE;\nlop3.b32 w0, w0, w12, w14, 0xFE;\nlop3.b32 %0, w0, w6, 1, 0xA8;\n}\n"
                           : "=r"(bad) : "r"(a0 + (slots & 15) * SLOT), "r"(bit) : "memory");
              if (__all_sync(0xffffffffu, bad == 0)) break;
              if (el) {
                fence_proxy_async_smem();
                mbar_expect_tx(cb, SLOT);
                tma_load_2d(sbase + (slots & 15) * SLOT, &tm_o, cb, srcb(jj, c) * 128 + (ph >> 1) * 64, mm * 128 + (ph ? 0 : S_LEN));
                RETRY_COUNT();
              }
              __syncwarp();
            }
            if (el) { mbar_arrive_local(bar_full + (c + (ph ? 25 + ph * 8 : 4)) * 8); if (lp == PRL * 4 && c == 0) PROFT(477); }
            __syncwarp();
          }
          if (ph) continue;
#pragma unroll 1
          for (int hp = 0; hp < 2; hp++) {
            const uint4* src = reinterpret_cast<const uint4*>(g_colsum[par][jj * 64 + hp * 32 + lane]);
            uint32_t bad;
            int it = 0;
            float c[6];
            do {
              bad = 0;
#pragma unroll
              for (int p = 0; p < 3; p++) {
                const uint4 v = ld_ll(src + ((par && p < 2) ? (hp ? -32 : 512) + p * 32 : p * 512));
                bad |= (v.y ^ ep1) | (v.w ^ ep1);
                c[2 * p] = __uint_as_float(v.x) + __uint_as_float(v.z); c[2 * p + 1] = __uint_as_float(v.y) + __uint_as_float(v.w);
              }
              bad &= 3;
              if (bad) __nanosleep(300);
            } while (bad && ++it < (1 << 16));
#pragma unroll
            for (int p = 0; p < 6; p++) {
              uint32_t h, m, lo;
              split3(c[p], h, m, lo);
              sts128(sbase + OFF_LNB + hp * 4096 + (p >> 1) * 1024 + lane * 32 + (p & 1) * 16, h | (m << 16), h | (lo << 16), h | (m << 16), lo | (m << 16));
            }
            fence_proxy_async_smem();
            __syncwarp();
            if (el) { mbar_arrive_local(hp ? bar_stat2 : bar_stat); if (hp == 0) PROFT(324 + l * 16); }
            __syncwarp();
          }
          continue;
        } else if (ph == 0) {
          mbar_wait_sl(bar_done + 24, par);
          const uint4* sp = reinterpret_cast<const uint4*>(g_stats + (size_t)(mm * 128) * 8) + lane;
#pragma unroll 1
          for (int hf = 0; hf < 4; hf++) {
            uint4 v[4];
            uint32_t bad;
            int it = 0;
            do {
              bad = 0;
#pragma unroll
              for (int i = 0; i < 4; i++) { v[i] = ld_ll(sp + (hf * 4 + i) * 32); bad |= (v[i].y ^ STAT_TAG(l)) | (v[i].w ^ STAT_TAG(l)); }
              bad &= 3;
              if (bad) __nanosleep(200);
            } while (bad && ++it < (1 << 16));
            __syncwarp();
            float mean = 0.f, m2 = 0.f;
#pragma unroll
            for (int i = 0; i < 4; i++) {
              float a = __uint_as_float(v[i].x) + __uint_as_float(v[i].z);
              a += __shfl_xor_sync(0xffffffffu, a, 1); a += __shfl_xor_sync(0xffffffffu, a, 2);
              a *= 0.125f;
              const float e0 = __uint_as_float(v[i].x) - a, e1 = __uint_as_float(v[i].z) - a;
              float q = fmaf(fmaf(e0, e0, e1 * e1), 128.f, __uint_as_float(v[i].y) + __uint_as_float(v[i].w));
              q += __shfl_xor_sync(0xffffffffu, q, 1); q += __shfl_xor_sync(0xffffffffu, q, 2);
              if ((lane & 3) == i) { mean = a; m2 = q; }
            }
            const uint32_t row = hf * 32 + (lane & 3) * 8 + (lane >> 2);
            uint32_t h, m, lo;
            split3(-0.5f * mean, h, m, lo);
            sts128(sbase + OFF_LNA + row * 16, h | (h << 16), m | (h << 16), lo | (m << 16), m | (lo << 16));
            sts32f(sbase + OFF_ST + row * 4, rsqrtf(m2 * (1.f / 1024.f) + 1e-5f));
          }
          fence_proxy_async_smem();
          __syncwarp();
          if (el) { mbar_arrive_local(bar_stat); PROFT(323 + l * 16); }
          __syncwarp();
#pragma unroll 1
          for (int i = 0; i < 8 - 4 * l; i++) {
            asm volatile("prefetch.global.L2 [%0];" :: "l"(i < 4 ? (l ? prm.wB_o : prm.wA_o) + (size_t)cta * 8192 + i * 2048 + lane * 64
                                                                 : prm.wB_qkv + (size_t)(cta * 8 + (i - 4) * 2 + (lane >> 4)) * 3072 + 2048 + (lane & 15) * 64));
            __nanosleep(PFGAP);
          }
          continue;
        }
        if (ph == 1) {
          if (par) continue;
#pragma unroll 1
          for (int i = 0; i < 2; i++) {
            if (i && lp + hw == 1 && NLAYERS > 1) {
#pragma unroll 1
              for (int c = 0; c < 8; c++) {
                if (!(c & 3)) asm volatile("bar.sync %0, 288;" :: "r"(BAR_WF + (c >> 2)) : "memory");
                if (el) {
                  tma_store_2d(&tm_wf, sbase + 11 * SLOT + c * 4096, (c < 4 ? 1024 : -128) + jj * 128 + (c >> 1) * 64, mm * 64 + (c & 1) * 32);
                  if ((c & 3) == 3) {
                    asm volatile("cp.async.bulk.commit_group;\ncp.async.bulk.wait_group.read 0;" ::: "memory");
                    mbar_arrive_local(bar_phi + (c >> 2) * 8);
                  } else __nanosleep(WFGAP);
                }
                __syncwarp();
              }
              if (el) { bulk_commit_wait(); signal_release(&g_flags.wfready[jj].v); PROFT(335); }
              __syncwarp();
            }
            mbar_wait_sl(bar_done + (i ? HW1 : (hw ? 19 : HW0)) * 8, 0);
            if (lp + hw == 2 && NLAYERS > 1) mbar_wait_sl(bar_phi, 1);
            const uint4* src = g_halo + (size_t)(mm * 8 + jj - 8) * 512 + i * 256 + hw * 128 + lane;
            uint4 v[4];
            int it = 0;
            bool ok;
            do {
#pragma unroll
              for (int j = 0; j < 4; j++) v[j] = mm ? ld_b128(src + j * 32) : make_uint4(H_BIT(l), 0, 0, 0);
              ok = __all_sync(0xffffffffu, (((v[0].x ^ H_BIT(l)) | (v[1].x ^ H_BIT(l)) | (v[2].x ^ H_BIT(l)) | (v[3].x ^ H_BIT(l))) & 1) == 0);
            } while (!ok && ++it < (1 << 16));
#pragma unroll
            for (int j = 0; j < 4; j++) sts128(sbase + OFF_S + hw * SLOT + j * 512 + lane * 16, v[j].x, v[j].y, v[j].z, v[j].w);
            __syncwarp();
            if (el) { mbar_arrive_local(bar_halo + hw * 8); PROFT(331 + l * 16 + i * 2 + hw); }
            __syncwarp();
          }
        } else if (hw == 0 && l < NLAYERS - 1) {
          bar_sync<BAR_X1, 288>();
          if (el) {
            PROFT(328 + l * 16);
            mbar_wait_sl(bar_full + XD * 8, par ^ 1);
            tma_store_2d(&tm_o, sbase + 11 * SLOT, jj * 128 + 64, mm * 128 + S_LEN);
            bulk_commit_wait();
            signal_release(&g_flags.xready[l + 1][mm].v);
            PROFT(330 + l * 16);
          }
          __syncwarp();
        }
      }
    }
    cluster_sync();
  } else {
    asm volatile("setmaxnreg.inc.sync.aligned.u32 232;");
    LOAD_EPOCH();
    const int wg = warp >> 2;
    const int r0 = warp * 16;
    const uint32_t pK = sbase + OFF_S, pV = sbase + OFF_S + SLOT;
#define PMASKS(on, bit) const uint32_t pm0 = ((on) && t == (g & 3) && (g >> 2) == (g & 1)), pm1 = ((on) && t == (g & 3) && (g >> 2) != (g & 1)), pbit = (bit)
#define PBIT0(w) (((w) & ~pm0) | (pbit & pm0))
#define PBIT1(w) (((w) & ~pm1) | (pbit & pm1))
#define LANE_CONSTS() \
    int lane; asm volatile("mov.u32 %0, %%laneid;" : "=r"(lane)); \
    const int g = lane >> 2, t = lane & 3; \
    const uint32_t srowoff = (r0 + (lane & 15)) * 128, lsw = (lane & 7) << 4, lhi = (lane >> 4) << 4, lsw2 = (lane & 6) << 3; \
    (void)g; (void)t; (void)srowoff; (void)lsw; (void)lhi; (void)lsw2;
    uint32_t stgp = 0, peer;
    asm volatile("mapa.shared::cluster.u32 %0, %1, %2;" : "=r"(peer) : "r"(sbase), "r"(rank ^ 1));
    peer -= sbase;
    const uint32_t dA0 = (((sbase & 0x3FFFF) + wg * 8192) >> 4) | 0x10000u, dB0 = ((sbase & 0x3FFFF) >> 4) | 0x2000000u;
    cluster_wait();
#define DESC(lo, hi) ((uint64_t)(uint32_t)(lo) | ((uint64_t)(hi) << 32))
#define STG_ARRIVE() { __syncwarp(); if (elect_one()) mbar_arrive_local(bar_stg); }
#define STG_WAIT() { mbar_wait(bar_stg, stgp); stgp ^= 1; }
#define PROFS() do {} while (0)
#define REL(addr) { if (elect_one()) { mbar_arrive_local(addr); asm volatile("mbarrier.arrive.shared::cluster.b64 _, [%0];" :: "r"((addr) + peer) : "memory"); } }
#define QSTEP(ACC, DA, SC, PRE) { \
      const uint32_t da = (DA), db = dB0 + (ub & 0x18) * (QST >> 7); \
      mbar_wait(ub, par); \
      PRE; \
      wgmma_fence(); \
      wgmma4_n192<SC>(ACC, da, db); \
      wgmma_commit(); PROFS(); }
#define QREL() { wgmma_wait<1>(); REL(ub + 376); ub += 8; }
#define RA_CUR (dA0 + (OFF_RA >> 4) + (ub & 0x18) * (SLOT >> 7))
#define PUMP1() { QSTEP(S1, RA_CUR, 1, {}); QREL(); }
#define PUMP0() { PUMP1(); SCHED_FENCE(); }
#define PUMP() if (h == 0) PUMP1()
#define WSTEP() { \
      const uint32_t s4 = (ub - bar_full - 256) >> 1; \
      const uint32_t da = dA0 + (((uint32_t)(WO_ASLOT(par) >> s4) & 15) << 10), db = dB0 + (((uint32_t)(WO_BSLOT >> s4) & 15) << 10); \
      mbar_wait(ub, par); \
      wgmma_fence(); \
      wgmma4_n128<1>(S1, da, db); \
      wgmma_commit(); PROFS(); \
      wgmma_wait<1>(); \
      if (s4) REL(ub + 376); \
      ub += 8; }
#define PUMPS(n) { _Pragma("unroll 1") for (int i_ = 0; i_ < (n); i_++) PUMP1(); }
#define SITE(n) { if ((BMASK >> (n)) & 1) PUMP1(); SCHED_FENCE(); }
#define LNSTEP(ACC, hh) { wgmma_fence(); wgmma_n192<1, 0>(ACC, make_desc(sbase + OFF_LNA + wg * 1024, 0, 128) ^ (1ull << 62), make_desc(sbase + OFF_LNB + (hh) * 4096, 0, 128) ^ (1ull << 62)); }
#define DRAIN_B(ACC) { \
      LANE_CONSTS(); \
      STAGE_V(ACC + 64, pV); \
      _Pragma("unroll") for (int i_ = 0; i_ < 64; i_++) st[i_] = ACC[i_]; \
      PIN(st, 64); }
#define WARP_STORE(tm, tile, col, row) { fence_proxy_async_smem(); __syncwarp(); \
      if (elect_one()) { tma_store_2d(tm, (tile) + r0 * 128, col, (row) + r0); asm volatile("cp.async.bulk.commit_group;" ::: "memory"); } __syncwarp(); }
#define PUBLISH_O() WARP_STORE(&tm_os, pO, jj * 128 + h * 64, mm * 128)
#define X_OUT(pc, on) { \
      PMASKS(on, X_BIT(l)); \
      _Pragma("unroll") for (int j = (pc) * 4; j < (pc) * 4 + 4; j++) \
        stsm_x4(pK + (pc) * SLOT + srowoff + ((((uint32_t)(j & 3) << 5) + lhi) ^ lsw), \
                PBIT0(pack_bf16(S1[j * 8 + 0], S1[j * 8 + 1])), PBIT0(pack_bf16(S1[j * 8 + 2], S1[j * 8 + 3])), \
                PBIT1(pack_bf16(S1[j * 8 + 4], S1[j * 8 + 5])), PBIT1(pack_bf16(S1[j * 8 + 6], S1[j * 8 + 7]))); }
#define REST_P1(SKEW) { \
      mbar_wait(bar_stat2, par); \
      LNSTEP(S1, 1); \
      _Pragma("unroll 1") while (ub < bar_full + 256) { \
        if (ub == bar_full + 256 - 8 * (SKEW) && wg == 0) bar_sync<BAR_SKEW, 256>(); \
        QSTEP(S1, RA_CUR, 1, {}); \
        if (ub == bar_full + 248 && wg == 1) bar_arrive<BAR_SKEW, 256>(); \
        QREL(); \
      } \
      mbar_wait(bar_done + (31 - (SKEW)) * 8, par);        \
      wgmma_wait<0>(); \
      ACC_FENCE(S1, 96); \
      REL(bar_done + 31 * 8); \
      PROF(13); }
#define FOLD(tile, rd) { \
          LANE_CONSTS(); \
          float d[32]; \
          ACC_DEF(d, 32); \
          mbar_wait(bar_phi, 0); \
          wgmma_fence(); \
          _Pragma("unroll") for (int i = 0; i < 2; i++) { \
            const uint64_t da = make_desc((tile) + wg * 8192 + i * 64, 16, 1024); \
            const uint64_t db = make_desc(sbase + OFF_PHI + wg * 4096 + i * 2048, 16, 512) ^ (3ull << 62); \
            wgmma_n32<0>(d + i * 16, da, db); wgmma_n32<1>(d + i * 16, da + 2, db + 64); \
          } \
          wgmma_commit(); \
          PUMP0(); \
          ACC_FENCE(d, 32); \
          bar_wg(wg); \
          _Pragma("unroll") for (int i = 0; i < 4; i++) { \
            const float* x = d + (i & 1) * 8 + (i >> 1) * 2; \
            if (rd) sts128((tile) + wg * 8192 + ((warp & 3) * 16 + (i >> 1) * 8 + g) * 128 + (((2 * t + (i & 1)) ^ g) << 4), \
                           pack_bf16(x[0], x[1]), pack_bf16(x[4], x[5]), pack_bf16(x[16], x[17]), pack_bf16(x[20], x[21])); \
            else stsm_x4((tile) + srowoff + ((((uint32_t)i << 5) + lhi) ^ lsw), pack_bf16(d[i * 8], d[i * 8 + 1]), pack_bf16(d[i * 8 + 2], d[i * 8 + 3]), \
                         pack_bf16(d[i * 8 + 4], d[i * 8 + 5]), pack_bf16(d[i * 8 + 6], d[i * 8 + 7])); \
          } \
          }
#define LOAD_X0(base) \
      _Pragma("unroll") for (int j = 0; j < 8; j++) { \
        uint32_t x0, x1, x2, x3; \
        ldsm_x4((base) + (j >> 2) * SLOT + srowoff + ((((uint32_t)(j & 3) << 5) + lhi) ^ lsw), x0, x1, x2, x3); \
        S1[j * 8 + 0] = bf_lo(x0); S1[j * 8 + 1] = bf_hi(x0); S1[j * 8 + 2] = bf_lo(x1); S1[j * 8 + 3] = bf_hi(x1); \
        S1[j * 8 + 4] = bf_lo(x2); S1[j * 8 + 5] = bf_hi(x2); S1[j * 8 + 6] = bf_lo(x3); S1[j * 8 + 7] = bf_hi(x3); \
      }
#define LOAD_X() { \
      wgmma_wait<0>(); \
      mbar_wait(bar_xr, par); \
      LOAD_X0(sbase + OFF_RA); \
      ACC_FENCE(S1, 64); \
      __syncwarp(); if (elect_one()) mbar_arrive_local(bar_lx); }

    float S1[96];
#pragma unroll
    for (int i = 0; i < 64; i++) S1[i] = 0.f;
#pragma unroll 1
    for (int l = 0; l < NLAYERS; l++) {
      const uint32_t par = l & 1;
      bar_wg(wg);
      PROF(0);
      uint32_t ub = bar_full;
      float S0[96];
      {
        LANE_CONSTS();
        ACC_DEF(S0, 96);
        QSTEP(S0, dA0 + (OFF_S >> 4), 0, {});
        ub += 8;
        PROF(1);
        if (l == 0) { mbar_wait(ub, 0); LOAD_X0(pK); }
        else { X_OUT(1, false); fence_proxy_async_smem(); }
        SCHED_FENCE();
        {
          float a0 = S1[0], a1 = S1[2], b0 = S1[1], b1 = S1[3];
#pragma unroll
          for (int i = 4; i < 64; i += 4) { a0 += S1[i]; b0 += S1[i + 1]; a1 += S1[i + 2]; b1 += S1[i + 3]; }
          a0 += b0; a1 += b1;
          a0 += __shfl_xor_sync(0xffffffffu, a0, 1); a1 += __shfl_xor_sync(0xffffffffu, a1, 1);
          a0 += __shfl_xor_sync(0xffffffffu, a0, 2); a1 += __shfl_xor_sync(0xffffffffu, a1, 2);
          a0 *= (1.f / 128.f); a1 *= (1.f / 128.f);
          asm volatile("" : "+f"(a0), "+f"(a1));
          bar_wg(wg);
          QSTEP(S0, dA0 + ((OFF_S + SLOT) >> 4), 1, wgmma_wait<0>());
          REL(ub + 376); ub += 8;
          SCHED_FENCE();
          float q0 = 0.f, q1 = 0.f;
          b0 = 0.f; b1 = 0.f;
#pragma unroll
          for (int i = 0; i < 64; i += 4) {
            const float d0 = S1[i] - a0, d1 = S1[i + 1] - a0, d2 = S1[i + 2] - a1, d3 = S1[i + 3] - a1;
            q0 = fmaf(d0, d0, q0); b0 = fmaf(d1, d1, b0); q1 = fmaf(d2, d2, q1); b1 = fmaf(d3, d3, b1);
          }
          q0 += b0; q1 += b1;
          q0 += __shfl_xor_sync(0xffffffffu, q0, 1); q1 += __shfl_xor_sync(0xffffffffu, q1, 1);
          q0 += __shfl_xor_sync(0xffffffffu, q0, 2); q1 += __shfl_xor_sync(0xffffffffu, q1, 2);
          if (t < 2) st_b64(g_stats + (size_t)(mm * 128 + r0 + g + t * 8) * 8 + jj, __float_as_uint(t ? a1 : a0), (__float_as_uint(t ? q1 : q0) & ~3u) | STAT_TAG(l));
        }
        if (l) { asm volatile("cp.async.bulk.wait_group 0;" ::: "memory"); bar_arrive<BAR_X1, 288>(); }
        ACC_DEF(S1, 96);
        QSTEP(S1, dA0 + (OFF_S >> 4), 0, {});
        QREL();
        QSTEP(S1, dA0 + ((OFF_S + SLOT) >> 4), 1, {});
        QREL();
#pragma unroll 1
        for (int i = 0; i < 14; i++) {
          QSTEP(S0, RA_CUR, 1, {});
          if (i == 0) PROF(2);
          QREL();
        }
      }
      LANE_CONSTS();
      mbar_wait(bar_stat, par);
      LNSTEP(S0, 0);
      wgmma_commit();
      const float rs0 = lds32f(sbase + OFF_ST + (r0 + g) * 4), rs1 = lds32f(sbase + OFF_ST + (r0 + g + 8) * 4);
      PUMP0();
      ACC_FENCE(S0, 96);
      PROF(3);
      if (!par) {
        constexpr uint32_t par = 0;
        uint32_t qa[16];
        uint32_t kf[32], vf[32];
#define DRAIN_A(ACC, hp, PMP) { \
          LANE_CONSTS(); \
          FRAG(kf + 16, ACC + 32, 0, (hp) * 2); \
          PMP; \
          FRAG(vf + 16, ACC + 64, 1, (hp) * 2 + 1); \
          _Pragma("unroll") for (int i_ = 0; i_ < 16; i_++) qa[i_] = pack_bf16(ACC[2 * i_], ACC[2 * i_ + 1]); \
          PINU(qa, 16); }
        DRAIN_A(S0, 0, PUMP0());
        if (l == 0 && NLAYERS > 1) {
#pragma unroll 1
          for (int rd = 1; rd >= 0; rd--) {
            FOLD(sbase + (12 - rd) * SLOT, rd);
            fence_proxy_async_smem();
            asm volatile("bar.arrive %0, 288;" :: "r"(BAR_WF + 1 - rd) : "memory");
          }
        }
        PUMPS(FPUMP);
        if (l == 0 && NLAYERS > 1) mbar_wait(bar_phi, 1);
#pragma unroll 1
        for (int h = 0; h < 2; h++) {
          const uint32_t pO = sbase + (h ? 3 : 12) * SLOT;
          PROF(4 + h * 12);
          LANE_CONSTS();
          FRAG_PUT(kf + 16, 10); FRAG_PUT(vf + 16, 11);
          STG_ARRIVE();
          if (h) { LOAD_X(); if (AW0) WSTEP(); } else PUMPS(HPUMP2);
          STG_WAIT();
          if (warp == 0) mbar_wait(bar_halo, h);
          FRAG_GET(kf, 10);
          PROF(5 + h * 12);
          float s[2][4][4];
#pragma unroll
          for (int ks = 0; ks < 2; ks++)
#pragma unroll
            for (int i = 0; i < 8; i++) {
              const int hh = (i >> 1) & 1, jb = (i & 1) + (~i >> 1 & 2);
              const uint32_t* b = kf + (jb >> 1) * 16 + hh * 8 + ks * 4 + (jb & 1) * 2;
              if (ks) mma_bf16(s[hh][jb], qa[hh * 8 + 4], qa[hh * 8 + 5], qa[hh * 8 + 6], qa[hh * 8 + 7], b[0], b[1]);
              else mma_bf16_z(s[hh][jb], qa[hh * 8], qa[hh * 8 + 1], qa[hh * 8 + 2], qa[hh * 8 + 3], b[0], b[1]);
            }
          PUMP();
          PROF(6 + h * 12);
          const bool e = g & 1, hb = (2 * t + (g & 1)) <= g;
          float va[2][2], vb[2][2], mx[2][2];
#pragma unroll
          for (int hh = 0; hh < 2; hh++) {
            va[hh][0] = e ? s[hh][1][1] : s[hh][1][0];
            vb[hh][0] = hb ? (e ? s[hh][2][1] : s[hh][2][0]) : (e ? s[hh][0][1] : s[hh][0][0]);
            va[hh][1] = e ? s[hh][2][3] : s[hh][2][2];
            vb[hh][1] = hb ? (e ? s[hh][3][3] : s[hh][3][2]) : (e ? s[hh][1][3] : s[hh][1][2]);
          }
          if (warp == 0 && mm == 0) {
#pragma unroll
            for (int hh = 0; hh < 2; hh++) { va[hh][0] = -INFINITY; if (!hb) { vb[hh][0] = -INFINITY; vb[hh][1] = -INFINITY; } }
          }
#pragma unroll
          for (int i = 0; i < 4; i++) mx[i >> 1][i & 1] = fmaxf(va[i >> 1][i & 1], vb[i >> 1][i & 1]);
#pragma unroll
          for (int o = 1; o <= 2; o <<= 1)
#pragma unroll
            for (int i = 0; i < 4; i++) mx[i >> 1][i & 1] = fmaxf(mx[i >> 1][i & 1], __shfl_xor_sync(0xffffffffu, mx[i >> 1][i & 1], o));
          const float sc0 = rs0 * (0.17677669529663687f * LOG2E), sc1 = rs1 * (0.17677669529663687f * LOG2E);
#pragma unroll
          for (int i = 0; i < 4; i++) {
            const float sc = (i & 1) ? sc1 : sc0, m = mx[i >> 1][i & 1];
            va[i >> 1][i & 1] = ex2((va[i >> 1][i & 1] - m) * sc); vb[i >> 1][i & 1] = ex2((vb[i >> 1][i & 1] - m) * sc);
            mx[i >> 1][i & 1] = va[i >> 1][i & 1] + vb[i >> 1][i & 1];
          }
          if (h == 0 && ASITE) { PIN(&va[0][0], 4); PIN(&vb[0][0], 4); PIN(&mx[0][0], 4); PUMP1(); }
          if (warp == 0) mbar_wait(bar_halo + 8, h);
          FRAG_GET(vf, 11);
#pragma unroll
          for (int o = 1; o <= 2; o <<= 1)
#pragma unroll
            for (int i = 0; i < 4; i++) mx[i >> 1][i & 1] += __shfl_xor_sync(0xffffffffu, mx[i >> 1][i & 1], o);
          const uint32_t selA = e ? 0x1044 : 0x4410, selB = e ? 0x3244 : 0x4432, selL = hb ? 0x4444 : selB, selH = hb ? selB : 0x4444;
          float o[2][4][4];
          uint32_t pa[2][8];
#pragma unroll
          for (int hh = 0; hh < 2; hh++) {
            const float i0 = rcp_fast(mx[hh][0]), i1 = rcp_fast(mx[hh][1]);
            const uint32_t w0 = pack_bf16(va[hh][0] * i0, vb[hh][0] * i0), w1 = pack_bf16(va[hh][1] * i1, vb[hh][1] * i1);
            pa[hh][0] = __byte_perm(w0, 0, selL); pa[hh][2] = __byte_perm(w0, 0, selA); pa[hh][3] = __byte_perm(w1, 0, selL);
            pa[hh][4] = __byte_perm(w0, 0, selH); pa[hh][5] = __byte_perm(w1, 0, selA); pa[hh][7] = __byte_perm(w1, 0, selH);
            pa[hh][1] = pa[hh][0] & pa[hh][4]; pa[hh][6] = pa[hh][3] & pa[hh][7];
          }
          PROF(7 + h * 12);
#pragma unroll
          for (int i = 0; i < 8; i++) mma_bf16_z(o[i >> 2][i & 3], pa[i >> 2][4], pa[i >> 2][5], pa[i >> 2][6], pa[i >> 2][7], vf[16 + 2 * i], vf[17 + 2 * i]);
#pragma unroll
          for (int i = 0; i < 8; i++) mma_bf16(o[i >> 2][i & 3], pa[i >> 2][0], pa[i >> 2][1], pa[i >> 2][2], pa[i >> 2][3], vf[2 * i], vf[2 * i + 1]);
          if (h == 0) PUMP1() else mbar_wait(bar_done + 30 * 8, par);
          if (NLAYERS > 1) mbar_wait(bar_phi + 8, 0);
#pragma unroll
          for (int i = 0; i < 4; i++) {
            const int hh = i >> 1, dp = i & 1;
            PMASKS(true, O_BIT(l));
            stsm_x4(pO + srowoff + ((hh * 64 + dp * 32 + lhi) ^ lsw), PBIT0(pack_bf16(o[hh][dp * 2][0], o[hh][dp * 2][1])), PBIT0(pack_bf16(o[hh][dp * 2][2], o[hh][dp * 2][3])),
                    PBIT1(pack_bf16(o[hh][dp * 2 + 1][0], o[hh][dp * 2 + 1][1])), PBIT1(pack_bf16(o[hh][dp * 2 + 1][2], o[hh][dp * 2 + 1][3])));
          }
          PUBLISH_O();
          PROF(11 + h * 12);
          if (h) break;
          REST_P1(ASKEW);
          asm volatile("cp.async.bulk.wait_group.read 0;" ::: "memory");
          DRAIN_A(S1, 1, {});
        }
      } else {
        constexpr uint32_t par = 1;
        float st[64];
        DRAIN_B(S0);
        if (warp < 2) sts128(sbase + OFF_ONES + warp * 512 + lane * 16, 0x3F803F80u, 0x3F803F80u, 0x3F803F80u, 0x3F803F80u);
        const float c0 = rs0 * LOG2E, c1 = rs1 * LOG2E;
#define KV_MMA(vs) { \
          const uint32_t dp = dA0 + 12 * 1024 - wg * 2560, dv = dA0 + (vs) * 1024 + ((OFF_ONES - (vs) * SLOT - 16) << 12) - wg * (512 << 16); \
          STG_WAIT(); \
          wgmma_fence(); \
          _Pragma("unroll") for (int ks = 0; ks < 8; ks++) { \
            const uint64_t a = DESC(dp + ks * 128, 0x40000040), b = DESC(dv + ks * (64 - (64 << 16)), 0x80000020); \
            if (ks == 0) wgmma_n40<0, 1>(kv, a, b); else wgmma_n40<1, 1>(kv, a, b); } \
          wgmma_commit(); }
#define KV_RED(hp) { \
          float* kvg = g_kv[l >> 1] + (jj * 4 + (hp) * 2 + wg) * KVH + ((warp & 3) * 32 + lane) * 4; \
          _Pragma("unroll") for (int i = 0; i < 5; i++) red_v4(kvg + i * 512, kv[i * 3], kv[i * 3 + 1], kv[i * 3 + 2], 1.f); \
          red_v4(kvg + 2560, kv[15], kv[16], kv[18], 1.f); }
#define KV_LOAD(hp) { \
          const uint4* kvg = reinterpret_cast<const uint4*>(g_kv[l >> 1] + (jj * 4 + (hp) * 2 + wg) * KVH) + (warp & 3) * 32 + lane; \
          _Pragma("unroll") for (int i = 0; i < 6; i++) v[i] = ld_b128(kvg + i * 128); }
#define KVV(i) __uint_as_float((i) % 3 == 0 ? v[(i) / 3].x : ((i) % 3 == 1 ? v[(i) / 3].y : v[(i) / 3].z))
#define KV_TILE(hp) { \
          _Pragma("unroll 1") for (int it = 0; it < (1 << 16); it++) { \
            if (__all_sync(0xffffffffu, (v[0].w & v[1].w & v[2].w & v[3].w & v[4].w & v[5].w) == 0x41800000u)) break; \
            RETRY_COUNT(); \
            KV_LOAD(hp); \
          } \
          PROF(25 + (hp)); \
          const uint32_t e = lane & 7, jt = ((lane >> 1) & 4) + (e >> 1); \
          const uint32_t row = ((((warp >> 1) ^ wg) & 1) << 5) + ((jt & 1) << 4) + ((warp & 1) << 3) + (jt & 6) + (e & 1); \
          const uint32_t kd = pV + wg * 8192 + row * 128, ksw = (row & 7) << 4; \
          _Pragma("unroll") for (int i = 0; i < 2; i++) \
            stsm_x4(kd + ((i * 32 + lhi) ^ ksw), pack_bf16(KVV(i * 8), KVV(i * 8 + 1)), pack_bf16(KVV(i * 8 + 2), KVV(i * 8 + 3)), \
                    pack_bf16(KVV(i * 8 + 4), KVV(i * 8 + 5)), pack_bf16(KVV(i * 8 + 6), KVV(i * 8 + 7))); \
          stsm_x4(kd + ((64u + lhi) ^ ksw), pack_bf16(KVV(16), 1.f), pack_bf16(KVV(17), 1.f), 0u, 0u); }
#pragma unroll 1
        for (int h = 0; h < 2; h++) {
          PROF(4 + h * 2);
          SITE(0);
          LANE_CONSTS();
          const uint32_t dsw = (uint32_t)(g ^ (2 * t)) << 4, dst = ((t & 2) ? pK : sbase + 12 * SLOT) + (r0 + g) * 128;
          float e[16], f[16];
          float mn0 = rmin16(st);
          asm volatile("" : "+f"(mn0)); SCHED_FENCE();
          float sa = exps16(e, st, -c0, mn0 * c0), mx0 = rmax16(st);
          asm volatile("" : "+f"(sa), "+f"(mx0)); PIN(e, 16); SITE(1);
          if (h) STG_WAIT();
          store16(e, sa, dst, dsw, 4);
          float sb = exps16(f, st, c0, -mx0 * c0), mn1 = rmin16(st + 2);
          asm volatile("" : "+f"(sb), "+f"(mn1)); PIN(f, 16); SITE(2);
          store16(f, sb, dst, dsw, 0);
          float sc = exps16(e, st + 2, -c1, mn1 * c1), mx1 = rmax16(st + 2);
          asm volatile("" : "+f"(sc), "+f"(mx1)); PIN(e, 16); SITE(3);
          store16(e, sc, dst + 1024, dsw, 4);
          float sd = exps16(f, st + 2, c1, -mx1 * c1);
          asm volatile("" : "+f"(sd)); PIN(f, 16); SITE(4);
          store16(f, sd, dst + 1024, dsw, 0);
          PROF(5 + h * 2);
          if (h) break;
          {
            float kv[20];
            ACC_DEF(kv, 20);
            fence_proxy_async_smem();
            STG_ARRIVE();
            KV_MMA(11);
            PUMP0();
            ACC_FENCE(kv, 20);
            KV_RED(0);
            STG_ARRIVE();
          }
#pragma unroll
          for (int i = 0; i < 32; i++) st[i] = st[32 + i];
        }
        float mq[8];
        uint4 v[6];
        {
          float kv[20];
          mbar_wait(bar_stat2, par);
          LNSTEP(S1, 1);
          ub = bar_full + 240;
          PUMP1();
          if (wg == 0) bar_sync<BAR_SKEW, 256>();
          QSTEP(S1, RA_CUR, 1, {});
          if (wg == 1) bar_arrive<BAR_SKEW, 256>();
          QREL();
          mbar_wait(bar_done + 30 * 8, par);
          wgmma_wait<0>();
          ACC_FENCE(S1, 96);
          if (!(RLATE & 2)) REL(bar_done + 31 * 8);
          PROF(13);
          LANE_CONSTS();
          STAGE_V(S1 + 64, sbase + 3 * SLOT);
          fence_proxy_async_smem();
          STG_ARRIVE();
          if (RLATE & 2) REL(bar_done + 31 * 8);
#pragma unroll
          for (int i = 0; i < 32; i++) st[i] = S1[i];
          PIN(st, 32);
          PROF(16);
          ACC_DEF(kv, 20);
          KV_MMA(3);
          SCHED_FENCE();
          KV_LOAD(0);
          extrema(mq, st, c0, c1);
          PIN(mq, 8);
          SCHED_FENCE();
          wgmma_wait<0>();
          ACC_FENCE(kv, 20);
          KV_RED(1);
          PROF(17);
        }
#pragma unroll 1
        for (int h = 0; h < 2; h++) {
          const uint32_t pO = sbase + (h ? 3 : 8) * SLOT;
          LANE_CONSTS();
          uint32_t fq[32];
          expp16(fq, st, -c0, mq[0], -c1, mq[1]); expp16(fq + 8, st, c0, mq[2], c1, mq[3]); PINU(fq, 16);
          PROF(18 + h * 14);
          SCHED_FENCE();
          if (h) {
            asm volatile("cp.async.bulk.wait_group.read 0;" ::: "memory");
            mbar_wait(bar_lx, par);
          }
          KV_TILE(h);
          fence_proxy_async_smem();
          STG_ARRIVE();
          SCHED_FENCE();
          expp16(fq + 16, st + 16, -c0, mq[4], -c1, mq[5]); PINU(fq + 16, 8);
          STG_WAIT();
          wgmma_wait<0>();
          ACC_FENCE(S1, 64);
          PROF(19 + h * 14);
          float o[4][20];
#define O_MMA(hh) { \
            const uint64_t db = make_desc(pV + (hh) * 8192, 16, 1024); \
            ACC_DEF(o[(hh) * 2], 20); ACC_DEF(o[(hh) * 2 + 1], 20); \
            wgmma_fence(); \
            wgmma_n40_rs<0>(o[(hh) * 2], fq + (hh) * 16, db + 256); wgmma_n40_rs<0>(o[(hh) * 2 + 1], fq + (hh) * 16 + 8, db); \
            wgmma_n40_rs<1>(o[(hh) * 2], fq + (hh) * 16 + 4, db + 384); wgmma_n40_rs<1>(o[(hh) * 2 + 1], fq + (hh) * 16 + 12, db + 128); \
            wgmma_commit(); }
          O_MMA(0);
          SCHED_FENCE();
          expp16(fq + 24, st + 16, c0, mq[6], c1, mq[7]); PINU(fq + 24, 8);
          SCHED_FENCE();
          PMASKS(true, O_BIT(l));
#pragma unroll
          for (int hh = 0; hh < 2; hh++) {
            if (hh && !OW) O_MMA(1);
            wgmma_wait<0>();
            ACC_FENCE(o[hh * 2], 20); ACC_FENCE(o[hh * 2 + 1], 20);
            if (!hh && OW) { O_MMA(1); SCHED_FENCE(); }
            const float* x = o[hh * 2];
            const float* y = o[hh * 2 + 1];
            const float rx0 = rcp_fast(x[17]), ry0 = rcp_fast(y[17]), rx1 = rcp_fast(x[19]), ry1 = rcp_fast(y[19]);
            const float i0 = rcp_fast(fmaf(x[16], rx0, y[16] * ry0) + 1e-6f), i1 = rcp_fast(fmaf(x[18], rx1, y[18] * ry1) + 1e-6f);
            const float ax0 = rx0 * i0, ay0 = ry0 * i0, ax1 = rx1 * i1, ay1 = ry1 * i1;
#pragma unroll
            for (int dp = 0; dp < 2; dp++)
              stsm_x4(pO + srowoff + ((hh * 64 + dp * 32 + lhi) ^ lsw),
                      PBIT0(pack_bf16(fmaf(x[dp * 8], ax0, y[dp * 8] * ay0), fmaf(x[dp * 8 + 1], ax0, y[dp * 8 + 1] * ay0))),
                      PBIT0(pack_bf16(fmaf(x[dp * 8 + 2], ax1, y[dp * 8 + 2] * ay1), fmaf(x[dp * 8 + 3], ax1, y[dp * 8 + 3] * ay1))),
                      PBIT1(pack_bf16(fmaf(x[dp * 8 + 4], ax0, y[dp * 8 + 4] * ay0), fmaf(x[dp * 8 + 5], ax0, y[dp * 8 + 5] * ay0))),
                      PBIT1(pack_bf16(fmaf(x[dp * 8 + 6], ax1, y[dp * 8 + 6] * ay1), fmaf(x[dp * 8 + 7], ax1, y[dp * 8 + 7] * ay1))));
          }
          PUBLISH_O();
          PROF(20 + h * 14);
          if (h) break;
#pragma unroll
          for (int i = 0; i < 32; i++) st[i] = S1[32 + i];
          PIN(st, 32);
          LOAD_X();
          bar_wg(wg);
          WSTEP();
          SCHED_FENCE();
          if (KVL == 0) KV_LOAD(1);
          extrema(mq, st, c0, c1);
          PIN(mq, 8);
          if (KVL == 1) { SCHED_FENCE(); KV_LOAD(1); }
          PROF(31);
        }
      }
      __syncwarp();
      if (elect_one()) mbar_arrive_local(bar_epi);
      bar_wg(wg);
#pragma unroll 1
      while (ub < bar_full + 384) {
        WSTEP();
        if (ub == bar_full + 8 * 41) { asm volatile("cp.async.bulk.wait_group.read 0;" ::: "memory"); PROF(35); }
        if (ub == bar_full + 8 * 42) PROF(36);
      }
      wgmma_wait<0>();
      ACC_FENCE(S1, 64);
      if (!RLATE) REL(bar_done + 47 * 8);
      PROF(37);
      {
        LANE_CONSTS();
        X_OUT(0, l < NLAYERS - 1);
        WARP_STORE(l < NLAYERS - 1 ? &tm_os : &tm_xo, pK, jj * 128, mm * 128 + (l < NLAYERS - 1 ? S_LEN : 0));
        if (RLATE) REL(bar_done + 47 * 8);
        if (l == NLAYERS - 1) {
          X_OUT(1, false);
          WARP_STORE(&tm_xo, pV, jj * 128 + 64, mm * 128);
          asm volatile("cp.async.bulk.wait_group 0;" ::: "memory");
        }
      }
#pragma unroll
      for (int i = 32; i < 64; i++) { uint32_t c; asm volatile("mov.b32 %0, %1;" : "=r"(c) : "f"(S1[i])); S1[i] = __uint_as_float(c); }
      PROF(38);
    }
    const int tid = threadIdx.x;
    if (tid == 0) {
      unsigned old = atomicAdd(&g_flags.done.v, 1);
      if (old == ep1 * NMAIN - 1) {
        asm volatile("st.relaxed.gpu.global.u32 [%0], %1;" :: "l"(&g_flags.epoch.v), "r"(ep1) : "memory");
      }
    }
    __syncwarp();
    cluster_sync();
  }
}

typedef CUresult (*PFN_encode)(CUtensorMap*, CUtensorMapDataType, cuuint32_t, void*, const cuuint64_t*, const cuuint64_t*,
                               const cuuint32_t*, const cuuint32_t*, CUtensorMapInterleave, CUtensorMapSwizzle,
                               CUtensorMapL2promotion, CUtensorMapFloatOOBfill);

CUtensorMap make_map(PFN_encode enc, const void* ptr, uint64_t inner, uint64_t outer, uint32_t box_inner, uint32_t box_outer,
                     CUtensorMapSwizzle swz = CU_TENSOR_MAP_SWIZZLE_128B) {
  CUtensorMap m;
  cuuint64_t dims[2] = {inner, outer};
  cuuint64_t strides[1] = {inner * 2};
  cuuint32_t box[2] = {box_inner, box_outer};
  cuuint32_t es[2] = {1, 1};
  enc(&m, CU_TENSOR_MAP_DATA_TYPE_BFLOAT16, 2, const_cast<void*>(ptr), dims, strides, box, es, CU_TENSOR_MAP_INTERLEAVE_NONE,
      swz, CU_TENSOR_MAP_L2_PROMOTION_L2_256B, CU_TENSOR_MAP_FLOAT_OOB_FILL_NONE);
  return m;
}

}

extern "C" void kernel_launch(void* const* d_in, const int* in_sizes, int n_in, void* d_out, int out_size) {
  (void)in_sizes; (void)n_in; (void)out_size;
  static PFN_encode enc = nullptr;
  if (!enc) {
    void* fn = nullptr;
    cudaDriverEntryPointQueryResult qr;
    cudaGetDriverEntryPoint("cuTensorMapEncodeTiled", &fn, cudaEnableDefault, &qr);
    enc = (PFN_encode)fn;
    cudaFuncSetAttribute(mega_kernel, cudaFuncAttributeMaxDynamicSharedMemorySize, SMEM_BYTES);
  }
  Params prm;
  prm.x0 = (const __nv_bfloat16*)d_in[0];
  prm.wA_qkv = (const __nv_bfloat16*)d_in[1];
  prm.wA_o = (const __nv_bfloat16*)d_in[2];
  prm.wB_qkv = (const __nv_bfloat16*)d_in[4];
  prm.wB_phi = (const __nv_bfloat16*)d_in[5];
  prm.wB_o = (const __nv_bfloat16*)d_in[6];
  prm.out = (__nv_bfloat16*)d_out;
  void *obuf = nullptr, *wf = nullptr;
  cudaGetSymbolAddress(&obuf, g_obuf);
  cudaGetSymbolAddress(&wf, g_wfold);
  CUtensorMap tm_x0 = make_map(enc, d_in[0], D_MODEL, S_LEN, 64, 128);
  CUtensorMap tm_xo = make_map(enc, d_out, D_MODEL, S_LEN, 64, 16);
  CUtensorMap tm_os = make_map(enc, obuf, D_MODEL, 2 * S_LEN, 64, 16);
  CUtensorMap tm_o = make_map(enc, obuf, D_MODEL, 2 * S_LEN, 64, 128);
  CUtensorMap tm_wf = make_map(enc, wf, 2048, D_MODEL, 64, 32);
  CUtensorMap tm_wqA = make_map(enc, d_in[1], 3 * D_MODEL, D_MODEL, 64, 32);
  CUtensorMap tm_wqB = make_map(enc, prm.wB_qkv, 3 * D_MODEL, D_MODEL, 64, 32);
  CUtensorMap tm_woA = make_map(enc, prm.wA_o, D_MODEL, D_MODEL, 64, 64);
  CUtensorMap tm_woB = make_map(enc, prm.wB_o, D_MODEL, D_MODEL, 64, 64);
  CUtensorMap tm_phi = make_map(enc, prm.wB_phi, 32, 1024, 32, 128, CU_TENSOR_MAP_SWIZZLE_64B);
  mega_kernel<<<NMAIN + NAUX, 384, SMEM_BYTES>>>(tm_x0, tm_xo, tm_os, tm_o, tm_wf, tm_wqA, tm_wqB, tm_woA, tm_woB, tm_phi, prm);
}
```

```cpp
#include <cuda_runtime.h>
#include <cuda.h>
#include <cuda_bf16.h>
#include <stdint.h>

#define NLAYERS 4

#define STAG1 0
#define HPUMP1 2
#define HPUMP2 1
#define ASKEW 2
#define FPUMP 3
#define PFGAP 100
#define POLLW 4
#define POLL0 0
#define POLLGAP 120
#define OW 1
#define NPOLL 4
#define AW0 1
#define RLATE 3
#define FSTART 0
#define MAPV 1
#define HW1 29
#define XPACE 0x06050401000000ull
#define XP0 4
#define HW0 18
#define XD 4
#define WFGAP 50
#define KT0 2
#define W23 0
#define AX 0
#define PF0 1
#define EARLY 2
#define KVL 1
#define BMASK 0x1F
#define ASITE 1
namespace {

constexpr int S_LEN = 2048, D_MODEL = 1024;
constexpr int NAUX = 4, NMAIN = 128;
constexpr int SLOT = 16384;
constexpr int QST = 24576;
constexpr int OFF_RA = 6 * SLOT, OFF_S = 10 * SLOT;
constexpr int OFF_HALO = 13 * SLOT, OFF_LNB = OFF_HALO  , OFF_ONES = OFF_HALO + 3072;
constexpr int OFF_ST = OFF_HALO + 7168  , OFF_PHI = OFF_HALO + 8192;
constexpr int OFF_BAR = 14 * SLOT;
constexpr int OFF_LNA = OFF_BAR + 1024;
constexpr int SMEM_BYTES = OFF_LNA + 2048;
#define WO_ASLOT(par) ((par) ? 0x9876CAB39876CA98ull : 0x98C76BA398C7698Cull)
constexpr unsigned long long WO_BSLOT = 0x5432105421054210ull;
__device__ __forceinline__ int srcb(int j, int i) { return (i + (i >= j)) & 7; }
__device__ __forceinline__ int kslice(int j, int i) { return i < 2 ? 2 * j + i : (i < 9 ? 2 * srcb(j, i - 2) : 2 * srcb(j, i - 9) + 1); }
__device__ __forceinline__ int wslice(int j, int s) { return 2 * ((s & 7) ? srcb(j, (s & 7) - 1) : j) + (s >> 3); }
constexpr int KVH = 6 * 128 * 4;

struct __align__(128) Flag { unsigned v; unsigned pad[31]; };
struct Flags {
  Flag xready[4][16];
  Flag wfready[8];
  Flag done;
  Flag epoch;
};

__device__ Flags g_flags;
__device__ __nv_bfloat16 g_obuf[2 * S_LEN * D_MODEL];
#define O_BIT(l) ((epoch * NLAYERS + (l) + 1) & 1u)
#define X_BIT(l) ((epoch * (NLAYERS - 1) + (l) + 1) & 1u)
__device__ __nv_bfloat16 g_wfold[D_MODEL * 2048];
__device__ uint4 g_halo[16 * 8 * 512];
__device__ __align__(128) float g_kv[2][32 * KVH];
__device__ __align__(128) uint2 g_colsum[2][1536][2];
__device__ __align__(128) uint2 g_stats[S_LEN * 8];
#define H_BIT(l) (NLAYERS > 2 ? (uint32_t)((l) == 0) : (ep1 & 1))
#define STAT_TAG(l) ((ep1 * NLAYERS + (l) + 1) & 3u)

#define RETRY_COUNT()
#define PRL 0
#define PRU 0
#define PROFL 1
#define PROFW 0
#define PROFT(i) do {} while (0)
#define PROF(i) do {} while (0)

__device__ __forceinline__ uint32_t smem_u32(const void* p) { return (uint32_t)__cvta_generic_to_shared(p); }
__device__ __forceinline__ bool elect_one() {
  uint32_t p;
  asm volatile("{\n.reg .pred p;\nelect.sync _|p, 0xffffffff;\nselp.u32 %0, 1, 0, p;\n}\n" : "=r"(p));
  return p != 0;
}
__device__ __forceinline__ void mbar_init(uint32_t bar, uint32_t cnt) {
  asm volatile("mbarrier.init.shared::cta.b64 [%0], %1;" :: "r"(bar), "r"(cnt));
}
__device__ __forceinline__ void mbar_expect_tx(uint32_t bar, uint32_t bytes) {
  asm volatile("mbarrier.arrive.expect_tx.shared::cta.b64 _, [%0], %1;" :: "r"(bar), "r"(bytes) : "memory");
}
#define mbar_wait(bar, parity) \
  asm volatile("{\n.reg .pred p, q;\nW_%=:\nmbarrier.try_wait.parity.shared::cta.b64 p, [%1], %2;\nadd.s32 %0, %0, -1;\n" \
               "setp.gt.and.s32 q, %0, 0, !p;\n@q bra.uni W_%=;\n}\n" : "+r"(budget) : "r"((uint32_t)(bar)), "r"((uint32_t)(parity)) : "memory")
#define mbar_wait_sl(bar, parity) \
  asm volatile("{\n.reg .pred p, q;\nW_%=:\nmbarrier.try_wait.parity.shared::cta.b64 p, [%1], %2, 20000;\nadd.s32 %0, %0, -64;\n" \
               "setp.gt.and.s32 q, %0, 0, !p;\n@q bra.uni W_%=;\n}\n" : "+r"(budget) : "r"((uint32_t)(bar)), "r"((uint32_t)(parity)) : "memory")
__device__ __forceinline__ void mbar_arrive_local(uint32_t bar) {
  asm volatile("mbarrier.arrive.shared::cta.b64 _, [%0];" :: "r"(bar) : "memory");
}
__device__ __forceinline__ void tma_load_2d(uint32_t dst, const CUtensorMap* tm, uint32_t bar, int c0, int c1) {
  asm volatile("cp.async.bulk.tensor.2d.shared::cluster.global.mbarrier::complete_tx::bytes [%0], [%1, {%3, %4}], [%2];"
               :: "r"(dst), "l"(tm), "r"(bar), "r"(c0), "r"(c1) : "memory");
}
__device__ __forceinline__ void tma_load_2d_mc(uint32_t dst, const CUtensorMap* tm, uint32_t bar, int c0, int c1) {
  asm volatile("cp.async.bulk.tensor.2d.shared::cluster.global.mbarrier::complete_tx::bytes.multicast::cluster [%0], [%1, {%3, %4}], [%2], %5;"
               :: "r"(dst), "l"(tm), "r"(bar), "r"(c0), "r"(c1), "h"((uint16_t)3) : "memory");
}
__device__ __forceinline__ void tma_store_2d(const CUtensorMap* tm, uint32_t src, int c0, int c1) {
  asm volatile("cp.async.bulk.tensor.2d.global.shared::cta.bulk_group [%0, {%2, %3}], [%1];"
               :: "l"(tm), "r"(src), "r"(c0), "r"(c1) : "memory");
}
__device__ __forceinline__ void bulk_commit_wait() {
  asm volatile("cp.async.bulk.commit_group;\ncp.async.bulk.wait_group 0;" ::: "memory");
}
__device__ __forceinline__ void prefetch_tmap(const CUtensorMap* tm) {
  asm volatile("prefetch.tensormap [%0];" :: "l"(tm) : "memory");
}
__device__ __forceinline__ void fence_proxy_async_global() { asm volatile("fence.proxy.async.global;" ::: "memory"); }
__device__ __forceinline__ void fence_proxy_async_smem() { asm volatile("fence.proxy.async.shared::cta;" ::: "memory"); }
__device__ __forceinline__ unsigned ld_relaxed(const unsigned* p) {
  unsigned v;
  asm volatile("ld.relaxed.gpu.global.u32 %0, [%1];" : "=r"(v) : "l"(p) : "memory");
  return v;
}
__device__ __forceinline__ void fence_acquire() { asm volatile("fence.acquire.gpu;" ::: "memory"); }
__device__ __forceinline__ void wait_flag(const unsigned* p, unsigned target) {
  int it = 0;
  while ((int)(ld_relaxed(p) - target) < 0 && ++it < (1 << 20)) {}
  fence_acquire();
}
__device__ __forceinline__ void signal_release(unsigned* p) {
  asm volatile("red.release.gpu.global.add.u32 [%0], 1;" :: "l"(p) : "memory");
}
template <int ID, int N> __device__ __forceinline__ void bar_arrive() { asm volatile("bar.arrive %0, %1;" :: "n"(ID), "n"(N) : "memory"); }
template <int ID, int N> __device__ __forceinline__ void bar_sync() { asm volatile("bar.sync %0, %1;" :: "n"(ID), "n"(N) : "memory"); }
__device__ __forceinline__ void bar_wg(int wg) { asm volatile("bar.sync %0, 128;" :: "r"(2 + wg) : "memory"); }
__device__ __forceinline__ void cluster_sync() {
  asm volatile("barrier.cluster.arrive.relaxed.aligned;\nbarrier.cluster.wait.aligned;" ::: "memory");
}
__device__ __forceinline__ void cluster_wait() { asm volatile("barrier.cluster.wait.acquire.aligned;" ::: "memory"); }
enum { BAR_X1 = 7, BAR_WF = 8  , BAR_SKEW = 10 };

__device__ __forceinline__ void wgmma_fence() { asm volatile("wgmma.fence.sync.aligned;" ::: "memory"); }
__device__ __forceinline__ void wgmma_commit() { asm volatile("wgmma.commit_group.sync.aligned;" ::: "memory"); }
template <int N> __device__ __forceinline__ void wgmma_wait() { asm volatile("wgmma.wait_group.sync.aligned %0;" :: "n"(N) : "memory"); }

template <int scale_d, int tnsp_b = 1> __device__ __forceinline__ void wgmma_n192(float* d, uint64_t descA, uint64_t descB) {
  asm volatile("{\n.reg .pred p;\nsetp.ne.b32 p, %98, 0;\n"
               "wgmma.mma_async.sync.aligned.m64n192k16.f32.bf16.bf16 {%0,%1,%2,%3,%4,%5,%6,%7,%8,%9,%10,%11,%12,%13,%14,%15,%16,%17,%18,%19,%20,%21,%22,%23,%24,%25,%26,%27,%28,%29,%30,%31,%32,%33,%34,%35,%36,%37,%38,%39,%40,%41,%42,%43,%44,%45,%46,%47,%48,%49,%50,%51,%52,%53,%54,%55,%56,%57,%58,%59,%60,%61,%62,%63,%64,%65,%66,%67,%68,%69,%70,%71,%72,%73,%74,%75,%76,%77,%78,%79,%80,%81,%82,%83,%84,%85,%86,%87,%88,%89,%90,%91,%92,%93,%94,%95}, %96, %97, p, 1, 1, 0, %99;\n}\n"
               : "+f"(d[0]), "+f"(d[1]), "+f"(d[2]), "+f"(d[3]), "+f"(d[4]), "+f"(d[5]), "+f"(d[6]), "+f"(d[7]), "+f"(d[8]), "+f"(d[9]), "+f"(d[10]), "+f"(d[11]), "+f"(d[12]), "+f"(d[13]), "+f"(d[14]), "+f"(d[15]), "+f"(d[16]), "+f"(d[17]), "+f"(d[18]), "+f"(d[19]), "+f"(d[20]), "+f"(d[21]), "+f"(d[22]), "+f"(d[23]), "+f"(d[24]), "+f"(d[25]), "+f"(d[26]), "+f"(d[27]), "+f"(d[28]), "+f"(d[29]), "+f"(d[30]), "+f"(d[31]), "+f"(d[32]), "+f"(d[33]), "+f"(d[34]), "+f"(d[35]), "+f"(d[36]), "+f"(d[37]), "+f"(d[38]), "+f"(d[39]), "+f"(d[40]), "+f"(d[41]), "+f"(d[42]), "+f"(d[43]), "+f"(d[44]), "+f"(d[45]), "+f"(d[46]), "+f"(d[47]), "+f"(d[48]), "+f"(d[49]), "+f"(d[50]), "+f"(d[51]), "+f"(d[52]), "+f"(d[53]), "+f"(d[54]), "+f"(d[55]), "+f"(d[56]), "+f"(d[57]), "+f"(d[58]), "+f"(d[59]), "+f"(d[60]), "+f"(d[61]), "+f"(d[62]), "+f"(d[63]), "+f"(d[64]), "+f"(d[65]), "+f"(d[66]), "+f"(d[67]), "+f"(d[68]), "+f"(d[69]), "+f"(d[70]), "+f"(d[71]), "+f"(d[72]), "+f"(d[73]), "+f"(d[74]), "+f"(d[75]), "+f"(d[76]), "+f"(d[77]), "+f"(d[78]), "+f"(d[79]), "+f"(d[80]), "+f"(d[81]), "+f"(d[82]), "+f"(d[83]), "+f"(d[84]), "+f"(d[85]), "+f"(d[86]), "+f"(d[87]), "+f"(d[88]), "+f"(d[89]), "+f"(d[90]), "+f"(d[91]), "+f"(d[92]), "+f"(d[93]), "+f"(d[94]), "+f"(d[95])
               : "l"(descA), "l"(descB), "n"(scale_d), "n"(tnsp_b));
}
template <int scale_d> __device__ __forceinline__ void wgmma4_n192(float* d, uint32_t da, uint32_t db) {
#define R_ "{%0,%1,%2,%3,%4,%5,%6,%7,%8,%9,%10,%11,%12,%13,%14,%15,%16,%17,%18,%19,%20,%21,%22,%23,%24,%25,%26,%27,%28,%29,%30,%31,%32,%33,%34,%35,%36,%37,%38,%39,%40,%41,%42,%43,%44,%45,%46,%47,%48,%49,%50,%51,%52,%53,%54,%55,%56,%57,%58,%59,%60,%61,%62,%63,%64,%65,%66,%67,%68,%69,%70,%71,%72,%73,%74,%75,%76,%77,%78,%79,%80,%81,%82,%83,%84,%85,%86,%87,%88,%89,%90,%91,%92,%93,%94,%95}"
  asm volatile("{\n.reg .pred p, q;\n.reg .b64 a, b;\nsetp.ne.b32 p, %98, 0;\nsetp.eq.b32 q, 0, 0;\nmov.b64 a, {%96, 0x40000040};\nmov.b64 b, {%97, 0x40000040};\n"
               "wgmma.mma_async.sync.aligned.m64n192k16.f32.bf16.bf16 " R_ ", a, b, p, 1, 1, 0, 1;\nadd.s64 a, a, 2;\nadd.s64 b, b, 128;\n"
               "wgmma.mma_async.sync.aligned.m64n192k16.f32.bf16.bf16 " R_ ", a, b, q, 1, 1, 0, 1;\nadd.s64 a, a, 2;\nadd.s64 b, b, 128;\n"
               "wgmma.mma_async.sync.aligned.m64n192k16.f32.bf16.bf16 " R_ ", a, b, q, 1, 1, 0, 1;\nadd.s64 a, a, 2;\nadd.s64 b, b, 128;\n"
               "wgmma.mma_async.sync.aligned.m64n192k16.f32.bf16.bf16 " R_ ", a, b, q, 1, 1, 0, 1;\n}\n"
               : "+f"(d[0]), "+f"(d[1]), "+f"(d[2]), "+f"(d[3]), "+f"(d[4]), "+f"(d[5]), "+f"(d[6]), "+f"(d[7]), "+f"(d[8]), "+f"(d[9]), "+f"(d[10]), "+f"(d[11]), "+f"(d[12]), "+f"(d[13]), "+f"(d[14]), "+f"(d[15]), "+f"(d[16]), "+f"(d[17]), "+f"(d[18]), "+f"(d[19]), "+f"(d[20]), "+f"(d[21]), "+f"(d[22]), "+f"(d[23]), "+f"(d[24]), "+f"(d[25]), "+f"(d[26]), "+f"(d[27]), "+f"(d[28]), "+f"(d[29]), "+f"(d[30]), "+f"(d[31]), "+f"(d[32]), "+f"(d[33]), "+f"(d[34]), "+f"(d[35]), "+f"(d[36]), "+f"(d[37]), "+f"(d[38]), "+f"(d[39]), "+f"(d[40]), "+f"(d[41]), "+f"(d[42]), "+f"(d[43]), "+f"(d[44]), "+f"(d[45]), "+f"(d[46]), "+f"(d[47]), "+f"(d[48]), "+f"(d[49]), "+f"(d[50]), "+f"(d[51]), "+f"(d[52]), "+f"(d[53]), "+f"(d[54]), "+f"(d[55]), "+f"(d[56]), "+f"(d[57]), "+f"(d[58]), "+f"(d[59]), "+f"(d[60]), "+f"(d[61]), "+f"(d[62]), "+f"(d[63]), "+f"(d[64]), "+f"(d[65]), "+f"(d[66]), "+f"(d[67]), "+f"(d[68]), "+f"(d[69]), "+f"(d[70]), "+f"(d[71]), "+f"(d[72]), "+f"(d[73]), "+f"(d[74]), "+f"(d[75]), "+f"(d[76]), "+f"(d[77]), "+f"(d[78]), "+f"(d[79]), "+f"(d[80]), "+f"(d[81]), "+f"(d[82]), "+f"(d[83]), "+f"(d[84]), "+f"(d[85]), "+f"(d[86]), "+f"(d[87]), "+f"(d[88]), "+f"(d[89]), "+f"(d[90]), "+f"(d[91]), "+f"(d[92]), "+f"(d[93]), "+f"(d[94]), "+f"(d[95])
               : "r"(da), "r"(db), "n"(scale_d));
#undef R_
}
template <int scale_d> __device__ __forceinline__ void wgmma4_n128(float* d, uint32_t da, uint32_t db) {
#define R_ "{%0,%1,%2,%3,%4,%5,%6,%7,%8,%9,%10,%11,%12,%13,%14,%15,%16,%17,%18,%19,%20,%21,%22,%23,%24,%25,%26,%27,%28,%29,%30,%31,%32,%33,%34,%35,%36,%37,%38,%39,%40,%41,%42,%43,%44,%45,%46,%47,%48,%49,%50,%51,%52,%53,%54,%55,%56,%57,%58,%59,%60,%61,%62,%63}"
  asm volatile("{\n.reg .pred p, q;\n.reg .b64 a, b;\nsetp.ne.b32 p, %66, 0;\nsetp.eq.b32 q, 0, 0;\nmov.b64 a, {%64, 0x40000040};\nmov.b64 b, {%65, 0x40000040};\n"
               "wgmma.mma_async.sync.aligned.m64n128k16.f32.bf16.bf16 " R_ ", a, b, p, 1, 1, 0, 1;\nadd.s64 a, a, 2;\nadd.s64 b, b, 128;\n"
               "wgmma.mma_async.sync.aligned.m64n128k16.f32.bf16.bf16 " R_ ", a, b, q, 1, 1, 0, 1;\nadd.s64 a, a, 2;\nadd.s64 b, b, 128;\n"
               "wgmma.mma_async.sync.aligned.m64n128k16.f32.bf16.bf16 " R_ ", a, b, q, 1, 1, 0, 1;\nadd.s64 a, a, 2;\nadd.s64 b, b, 128;\n"
               "wgmma.mma_async.sync.aligned.m64n128k16.f32.bf16.bf16 " R_ ", a, b, q, 1, 1, 0, 1;\n}\n"
               : "+f"(d[0]), "+f"(d[1]), "+f"(d[2]), "+f"(d[3]), "+f"(d[4]), "+f"(d[5]), "+f"(d[6]), "+f"(d[7]), "+f"(d[8]), "+f"(d[9]), "+f"(d[10]), "+f"(d[11]), "+f"(d[12]), "+f"(d[13]), "+f"(d[14]), "+f"(d[15]), "+f"(d[16]), "+f"(d[17]), "+f"(d[18]), "+f"(d[19]), "+f"(d[20]), "+f"(d[21]), "+f"(d[22]), "+f"(d[23]), "+f"(d[24]), "+f"(d[25]), "+f"(d[26]), "+f"(d[27]), "+f"(d[28]), "+f"(d[29]), "+f"(d[30]), "+f"(d[31]), "+f"(d[32]), "+f"(d[33]), "+f"(d[34]), "+f"(d[35]), "+f"(d[36]), "+f"(d[37]), "+f"(d[38]), "+f"(d[39]), "+f"(d[40]), "+f"(d[41]), "+f"(d[42]), "+f"(d[43]), "+f"(d[44]), "+f"(d[45]), "+f"(d[46]), "+f"(d[47]), "+f"(d[48]), "+f"(d[49]), "+f"(d[50]), "+f"(d[51]), "+f"(d[52]), "+f"(d[53]), "+f"(d[54]), "+f"(d[55]), "+f"(d[56]), "+f"(d[57]), "+f"(d[58]), "+f"(d[59]), "+f"(d[60]), "+f"(d[61]), "+f"(d[62]), "+f"(d[63])
               : "r"(da), "r"(db), "n"(scale_d));
#undef R_
}
template <int scale_d> __device__ __forceinline__ void wgmma_n32(float* d, uint64_t descA, uint64_t descB) {
  asm volatile("{\n.reg .pred p;\nsetp.ne.b32 p, %18, 0;\n"
               "wgmma.mma_async.sync.aligned.m64n32k16.f32.bf16.bf16 {%0,%1,%2,%3,%4,%5,%6,%7,%8,%9,%10,%11,%12,%13,%14,%15}, %16, %17, p, 1, 1, 0, 1;\n}\n"
               : "+f"(d[0]), "+f"(d[1]), "+f"(d[2]), "+f"(d[3]), "+f"(d[4]), "+f"(d[5]), "+f"(d[6]), "+f"(d[7]), "+f"(d[8]), "+f"(d[9]), "+f"(d[10]), "+f"(d[11]), "+f"(d[12]), "+f"(d[13]), "+f"(d[14]), "+f"(d[15])
               : "l"(descA), "l"(descB), "n"(scale_d));
}
template <int scale_d, int tnsp_a> __device__ __forceinline__ void wgmma_n40(float* d, uint64_t descA, uint64_t descB) {
  asm volatile("{\n.reg .pred p;\nsetp.ne.b32 p, %22, 0;\n"
               "wgmma.mma_async.sync.aligned.m64n40k16.f32.bf16.bf16 {%0,%1,%2,%3,%4,%5,%6,%7,%8,%9,%10,%11,%12,%13,%14,%15,%16,%17,%18,%19}, %20, %21, p, 1, 1, %23, 1;\n}\n"
               : "+f"(d[0]), "+f"(d[1]), "+f"(d[2]), "+f"(d[3]), "+f"(d[4]), "+f"(d[5]), "+f"(d[6]), "+f"(d[7]), "+f"(d[8]), "+f"(d[9]), "+f"(d[10]), "+f"(d[11]), "+f"(d[12]), "+f"(d[13]), "+f"(d[14]), "+f"(d[15]), "+f"(d[16]), "+f"(d[17]), "+f"(d[18]), "+f"(d[19])
               : "l"(descA), "l"(descB), "n"(scale_d), "n"(tnsp_a));
}
template <int scale_d> __device__ __forceinline__ void wgmma_n40_rs(float* d, const uint32_t* a, uint64_t descB) {
  asm volatile("{\n.reg .pred p;\nsetp.ne.b32 p, %25, 0;\n"
               "wgmma.mma_async.sync.aligned.m64n40k16.f32.bf16.bf16 {%0,%1,%2,%3,%4,%5,%6,%7,%8,%9,%10,%11,%12,%13,%14,%15,%16,%17,%18,%19}, {%20,%21,%22,%23}, %24, p, 1, 1, 1;\n}\n"
               : "+f"(d[0]), "+f"(d[1]), "+f"(d[2]), "+f"(d[3]), "+f"(d[4]), "+f"(d[5]), "+f"(d[6]), "+f"(d[7]), "+f"(d[8]), "+f"(d[9]), "+f"(d[10]), "+f"(d[11]), "+f"(d[12]), "+f"(d[13]), "+f"(d[14]), "+f"(d[15]), "+f"(d[16]), "+f"(d[17]), "+f"(d[18]), "+f"(d[19])
               : "r"(a[0]), "r"(a[1]), "r"(a[2]), "r"(a[3]), "l"(descB), "n"(scale_d));
}
__device__ __forceinline__ uint64_t make_desc(uint32_t addr, uint32_t lbo_bytes, uint32_t sbo_bytes) {
  return (uint64_t)((addr & 0x3FFFF) >> 4) | ((uint64_t)(lbo_bytes >> 4) << 16) | ((uint64_t)(sbo_bytes >> 4) << 32) | (1ull << 62);
}

__device__ __forceinline__ void ldsm_x4(uint32_t addr, uint32_t& r0, uint32_t& r1, uint32_t& r2, uint32_t& r3) {
  asm volatile("ldmatrix.sync.aligned.m8n8.x4.shared.b16 {%0,%1,%2,%3}, [%4];" : "=r"(r0), "=r"(r1), "=r"(r2), "=r"(r3) : "r"(addr) : "memory");
}
__device__ __forceinline__ void ldsm_x4_t(uint32_t addr, uint32_t& r0, uint32_t& r1, uint32_t& r2, uint32_t& r3) {
  asm volatile("ldmatrix.sync.aligned.m8n8.x4.trans.shared.b16 {%0,%1,%2,%3}, [%4];" : "=r"(r0), "=r"(r1), "=r"(r2), "=r"(r3) : "r"(addr) : "memory");
}
__device__ __forceinline__ void stsm_x4(uint32_t addr, uint32_t r0, uint32_t r1, uint32_t r2, uint32_t r3) {
  asm volatile("stmatrix.sync.aligned.m8n8.x4.shared.b16 [%0], {%1,%2,%3,%4};" :: "r"(addr), "r"(r0), "r"(r1), "r"(r2), "r"(r3) : "memory");
}
__device__ __forceinline__ void sts128(uint32_t addr, uint32_t a, uint32_t b, uint32_t c, uint32_t d) {
  asm volatile("st.shared.v4.u32 [%0], {%1,%2,%3,%4};" :: "r"(addr), "r"(a), "r"(b), "r"(c), "r"(d) : "memory");
}
__device__ __forceinline__ float lds32f(uint32_t addr) {
  float v;
  asm volatile("ld.shared.f32 %0, [%1];" : "=f"(v) : "r"(addr) : "memory");
  return v;
}
__device__ __forceinline__ void sts32f(uint32_t addr, float a) {
  asm volatile("st.shared.f32 [%0], %1;" :: "r"(addr), "f"(a) : "memory");
}
__device__ __forceinline__ void mma_bf16(float (&c)[4], uint32_t a0, uint32_t a1, uint32_t a2, uint32_t a3, uint32_t b0, uint32_t b1) {
  asm volatile("mma.sync.aligned.m16n8k16.row.col.f32.bf16.bf16.f32 {%0,%1,%2,%3}, {%4,%5,%6,%7}, {%8,%9}, {%0,%1,%2,%3};"
               : "+f"(c[0]), "+f"(c[1]), "+f"(c[2]), "+f"(c[3]) : "r"(a0), "r"(a1), "r"(a2), "r"(a3), "r"(b0), "r"(b1));
}
__device__ __forceinline__ void mma_bf16_z(float (&c)[4], uint32_t a0, uint32_t a1, uint32_t a2, uint32_t a3, uint32_t b0, uint32_t b1) {
  asm volatile("mma.sync.aligned.m16n8k16.row.col.f32.bf16.bf16.f32 {%0,%1,%2,%3}, {%4,%5,%6,%7}, {%8,%9}, {%10,%10,%10,%10};"
               : "=f"(c[0]), "=f"(c[1]), "=f"(c[2]), "=f"(c[3]) : "r"(a0), "r"(a1), "r"(a2), "r"(a3), "r"(b0), "r"(b1), "f"(0.f));
}
__device__ __forceinline__ uint32_t movm_t(uint32_t v) {
  uint32_t r;
  asm volatile("movmatrix.sync.aligned.m8n8.trans.b16 %0, %1;" : "=r"(r) : "r"(v));
  return r;
}
__device__ __forceinline__ uint32_t pack_bf16(float lo, float hi) {
  uint32_t r;
  asm("cvt.rn.bf16x2.f32 %0, %1, %2;" : "=r"(r) : "f"(hi), "f"(lo));
  return r;
}
__device__ __forceinline__ float bf_lo(uint32_t v) { return __uint_as_float(v << 16); }
__device__ __forceinline__ float bf_hi(uint32_t v) { return __uint_as_float(v & 0xFFFF0000u); }
__device__ __forceinline__ void split3(float x, uint32_t& h, uint32_t& m, uint32_t& l) {
  h = pack_bf16(x, 0.f); x -= bf_lo(h);
  m = pack_bf16(x, 0.f); x -= bf_lo(m);
  l = pack_bf16(x, 0.f);
}
__device__ __forceinline__ float ex2(float x) { float r; asm("ex2.approx.ftz.f32 %0, %1;" : "=f"(r) : "f"(x)); return r; }
__device__ __forceinline__ float rcp_fast(float x) { float r; asm("rcp.approx.ftz.f32 %0, %1;" : "=f"(r) : "f"(x)); return r; }
__device__ __forceinline__ void red_v4(float* p, float a, float b, float c, float d) {
  asm volatile("red.global.add.v4.f32 [%0], {%1, %2, %3, %4};" :: "l"(p), "f"(a), "f"(b), "f"(c), "f"(d) : "memory");
}
__device__ __forceinline__ uint4 ld_ll(const uint4* p) {
  uint4 v;
  asm volatile("{\n.reg .b64 a, b;\nld.relaxed.gpu.global.v2.b64 {a, b}, [%4];\nmov.b64 {%0, %1}, a;\nmov.b64 {%2, %3}, b;\n}\n"
               : "=r"(v.x), "=r"(v.y), "=r"(v.z), "=r"(v.w) : "l"(p) : "memory");
  return v;
}
__device__ __forceinline__ void st_b64(uint2* p, uint32_t a, uint32_t b) {
  asm volatile("{\n.reg .b64 v;\nmov.b64 v, {%1, %2};\nst.relaxed.gpu.global.b64 [%0], v;\n}\n" :: "l"(p), "r"(a), "r"(b) : "memory");
}
__device__ __forceinline__ void st_b128(uint4* p, uint32_t a, uint32_t b, uint32_t c, uint32_t d) {
  asm volatile("{\n.reg .b128 v;\nmov.b128 v, {%1, %2, %3, %4};\nst.relaxed.gpu.global.b128 [%0], v;\n}\n" :: "l"(p), "r"(a), "r"(b), "r"(c), "r"(d) : "memory");
}
__device__ __forceinline__ uint4 ld_b128(const uint4* p) {
  uint4 v;
  asm volatile("{\n.reg .b128 v;\nld.relaxed.gpu.global.b128 v, [%4];\nmov.b128 {%0, %1, %2, %3}, v;\n}\n" : "=r"(v.x), "=r"(v.y), "=r"(v.z), "=r"(v.w) : "l"(p) : "memory");
  return v;
}

constexpr float LOG2E = 1.4426950408889634f;

struct Params {
  const __nv_bfloat16* x0;
  const __nv_bfloat16* wA_qkv;
  const __nv_bfloat16* wA_o;
  const __nv_bfloat16* wB_qkv;
  const __nv_bfloat16* wB_phi;
  const __nv_bfloat16* wB_o;
  __nv_bfloat16* out;
};

#define ACC_DEF(d, n) _Pragma("unroll") for (int i_ = 0; i_ < (n); i_++) asm volatile("" : "=f"(d[i_]))
#define ACC_FENCE(d, n) _Pragma("unroll") for (int i_ = 0; i_ < (n); i_++) asm volatile("" : "+f"(d[i_]) :: "memory")
#define PIN(a, n) _Pragma("unroll") for (int i_ = 0; i_ < (n); i_++) asm volatile("" : "+f"((a)[i_]))
#define PINU(a, n) _Pragma("unroll") for (int i_ = 0; i_ < (n); i_++) asm volatile("" : "+r"((a)[i_]))

#define STAGE_V(acc, p0) { \
    _Pragma("unroll") for (int j_ = 0; j_ < 4; j_++) { \
      const float* a_ = (acc) + j_ * 8; \
      stsm_x4((p0) + (j_ >> 1) * 8192 + (srowoff >> 1) + ((((uint32_t)(j_ & 1) << 5) + lhi) ^ lsw2), \
              pack_bf16(rs0 * a_[0], rs0 * a_[1]), pack_bf16(rs1 * a_[2], rs1 * a_[3]), pack_bf16(rs0 * a_[4], rs0 * a_[5]), pack_bf16(rs1 * a_[6], rs1 * a_[7])); } }
#define FRAG(dst, acc, TR, grp) { \
    _Pragma("unroll") for (int i_ = 0; i_ < 16; i_++) { \
      const float r_ = (i_ & 1) ? rs1 : rs0; \
      const uint32_t w_ = pack_bf16(r_ * (acc)[2 * i_], r_ * (acc)[2 * i_ + 1]); \
      if (TR) (dst)[i_] = movm_t(w_); else (dst)[(i_ & 12) + (i_ & 1) * 2 + ((i_ >> 1) & 1)] = w_; } \
    if (warp == 7 && mm < 15) { \
      _Pragma("unroll") for (int j_ = 0; j_ < 4; j_++) \
        st_b128(g_halo + (size_t)(mm * 8 + jj) * 512 + ((grp) * 4 + j_) * 32 + lane, ((dst)[j_ * 4] & ~1u) | H_BIT(l), (dst)[j_ * 4 + 1], (dst)[j_ * 4 + 2], (dst)[j_ * 4 + 3]); } \
    PINU(dst, 16); }
#define FRAG_PUT(src, slot) if (warp < 7) { _Pragma("unroll") for (int j_ = 0; j_ < 4; j_++) \
      sts128(sbase + (slot) * SLOT + 2048 + warp * 2048 + j_ * 512 + lane * 16, (src)[j_ * 4], (src)[j_ * 4 + 1], (src)[j_ * 4 + 2], (src)[j_ * 4 + 3]); }
#define FRAG_GET(dst, slot) { _Pragma("unroll") for (int j_ = 0; j_ < 4; j_++) \
      asm volatile("ld.shared.v4.u32 {%0, %1, %2, %3}, [%4];" : "=r"((dst)[j_ * 4]), "=r"((dst)[j_ * 4 + 1]), "=r"((dst)[j_ * 4 + 2]), "=r"((dst)[j_ * 4 + 3]) \
                   : "r"(sbase + (slot) * SLOT + warp * 2048 + j_ * 512 + lane * 16) : "memory"); }
#define RW(j) (((j) >> 1) * 4 + ((j) & 1))
__device__ __forceinline__ float rmax16(const float* p) {
  float m[4];
#pragma unroll
  for (int j = 0; j < 4; j++) m[j] = fmaxf(fmaxf(p[RW(j)], p[RW(j + 4)]), fmaxf(p[RW(j + 8)], p[RW(j + 12)]));
  const float r = fmaxf(fmaxf(m[0], m[1]), fmaxf(m[2], m[3]));
  return fmaxf(r, __shfl_xor_sync(0xffffffffu, r, 1));
}
__device__ __forceinline__ float rmin16(const float* p) {
  float m[4];
#pragma unroll
  for (int j = 0; j < 4; j++) m[j] = fminf(fminf(p[RW(j)], p[RW(j + 4)]), fminf(p[RW(j + 8)], p[RW(j + 12)]));
  const float r = fminf(fminf(m[0], m[1]), fminf(m[2], m[3]));
  return fminf(r, __shfl_xor_sync(0xffffffffu, r, 1));
}
__device__ __forceinline__ float exps16(float* o, const float* p, float c, float b) {
  float s[4];
#pragma unroll
  for (int j = 0; j < 16; j++) { o[j] = ex2(fmaf(p[RW(j)], c, b)); if (j < 4) s[j] = o[j]; else s[j & 3] += o[j]; }
  return (s[0] + s[1]) + (s[2] + s[3]);
}
__device__ __forceinline__ void store16(const float* e, float sum, uint32_t dst, uint32_t dsw, int c0) {
  const float inv = rcp_fast(sum + __shfl_xor_sync(0xffffffffu, sum, 1));
#pragma unroll
  for (int j = 0; j < 2; j++)
    sts128(dst + (((c0 + j) << 4) ^ dsw), pack_bf16(e[j * 8] * inv, e[j * 8 + 1] * inv), pack_bf16(e[j * 8 + 2] * inv, e[j * 8 + 3] * inv),
           pack_bf16(e[j * 8 + 4] * inv, e[j * 8 + 5] * inv), pack_bf16(e[j * 8 + 6] * inv, e[j * 8 + 7] * inv));
}
__device__ __forceinline__ void expp16(uint32_t* o, const float* p, float c0, float b0, float c1, float b1) {
#pragma unroll
  for (int j = 0; j < 8; j++) {
    const float c = (j & 1) ? c1 : c0, b = (j & 1) ? b1 : b0;
    o[j] = pack_bf16(ex2(fmaf(p[2 * j], c, b)), ex2(fmaf(p[2 * j + 1], c, b)));
  }
}
__device__ __forceinline__ void extrema(float* m, const float* p, float c0, float c1) {
#pragma unroll
  for (int i = 0; i < 4; i++) {
    const float* q = p + (i >> 1) * 16 + (i & 1) * 2;
    m[(i >> 1) * 4 + (i & 1)] = fminf(fminf(fminf(q[0], q[1]), fminf(q[4], q[5])), fminf(fminf(q[8], q[9]), fminf(q[12], q[13])));
    m[(i >> 1) * 4 + (i & 1) + 2] = fmaxf(fmaxf(fmaxf(q[0], q[1]), fmaxf(q[4], q[5])), fmaxf(fmaxf(q[8], q[9]), fmaxf(q[12], q[13])));
  }
#pragma unroll
  for (int o = 1; o <= 2; o <<= 1)
#pragma unroll
    for (int i = 0; i < 8; i++) { const float x = __shfl_xor_sync(0xffffffffu, m[i], o); m[i] = (i & 2) ? fmaxf(m[i], x) : fminf(m[i], x); }
#pragma unroll
  for (int i = 0; i < 8; i++) m[i] *= ((i & 2) ? -1.f : 1.f) * ((i & 1) ? c1 : c0);
}
#define SCHED_FENCE() asm volatile("pmevent 0;" ::: "memory")

__global__ void __cluster_dims__(2, 1, 1) __launch_bounds__(384, 1)
mega_kernel(const __grid_constant__ CUtensorMap tm_x0, const __grid_constant__ CUtensorMap tm_xo, const __grid_constant__ CUtensorMap tm_os,
            const __grid_constant__ CUtensorMap tm_o, const __grid_constant__ CUtensorMap tm_wf,
            const __grid_constant__ CUtensorMap tm_wqA, const __grid_constant__ CUtensorMap tm_wqB,
            const __grid_constant__ CUtensorMap tm_woA, const __grid_constant__ CUtensorMap tm_woB,
            const __grid_constant__ CUtensorMap tm_phi, const Params prm) {
  extern __shared__ __align__(1024) uint8_t smem_raw[];
  const uint32_t sbase = smem_u32(smem_raw);
  const uint32_t bar_full = sbase + OFF_BAR;
  const uint32_t bar_done = bar_full + 384;
  const uint32_t bar_stat = bar_full + 768, bar_stat2 = bar_full + 776, bar_epi = bar_full + 784, bar_phi = bar_full + 936  , bar_halo = bar_full + 904  ;
  const uint32_t bar_xr = bar_full + 800, bar_lx = bar_full + 808, bar_stg = bar_full + 832;
  const uint32_t bar_chk = bar_full + 848;

  const int warp = __shfl_sync(0xffffffffu, threadIdx.x >> 5, 0), lane = threadIdx.x & 31;
  uint32_t rank;
  asm volatile("mov.u32 %0, %%cluster_ctarank;" : "=r"(rank));
  const int aux = (int)blockIdx.x - NMAIN, tp = (int)(blockIdx.x >> 1) - 4;
  const int gp = tp < 0 ? 0 : (tp < 32 ? tp & 7 : 1 + (tp - 32) % 7), me = tp < 0 ? tp + 8 : (tp < 32 ? tp >> 3 : 4 + (tp - 32) / 7);
  const int jj = me, cc = gp;
  const int cta = aux >= 0 ? -1 : (cc * 8 + jj) * 2 + (int)rank;
  const int mm = cc * 2 + (int)rank;

#define LOAD_EPOCH() const unsigned epoch = ld_relaxed(&g_flags.epoch.v), ep1 = epoch + 1; (void)epoch
  int budget = 1 << 22;

  if (cta >= 0) {
    if (warp >= 8 && warp < 8 + EARLY && elect_one()) {
      const int u = warp - 8;
      const uint32_t fb = bar_full + u * 8;
      mbar_init(fb, 1);
      asm volatile("fence.mbarrier_init.release.cluster;" ::: "memory");
      fence_proxy_async_smem();
      mbar_expect_tx(fb, u < 2 ? QST + SLOT : QST);
      if (u < 2) tma_load_2d(sbase + OFF_S + u * SLOT, &tm_x0, fb, jj * 128 + u * 64, mm * 128);
#pragma unroll
      for (int i = 0; i < 6; i++) tma_load_2d(sbase + u * QST + i * 4096, &tm_wqA, fb, jj * 128 + (u >> 1) * 64 + (i >> 1) * 1024, jj * 128 + (u & 1) * 64 + (i & 1) * 32);
      if (u == 0) PROFT(472);
    }
    __syncwarp();
    {
      const int tx = threadIdx.x;
      const __nv_bfloat16* pf = (tx < 128) ? prm.x0 + (size_t)(mm * 128 + tx) * D_MODEL + jj * 128
                                           : prm.wA_qkv + (size_t)(jj * 128 + (tx & 63)) * 3072 + ((tx - 128) >> 6) * 1024 + jj * 128 + rank * 64;
      if (tx < 320) { if (PF0) asm volatile("prefetch.global.L2 [%0];" :: "l"(pf)); }
      else if (tx == 320) prefetch_tmap(&tm_x0);
      else if (tx == 352) prefetch_tmap(&tm_wqA);
      else if (tx == 383) asm volatile("prefetch.global.L2 [%0];" :: "l"(&g_flags.epoch.v));
    }
    if (elect_one()) {
#pragma unroll
      for (int i = 0; i < 4; i++) {
        const int u = warp * 4 + i;
        if (u >= EARLY) mbar_init(bar_full + u * 8, ((u >= 4 && u < 11) || (u > 32 && u != 40)) ? 2 : 1); mbar_init(bar_done + u * 8, 16);
      }
      mbar_init(bar_stat + warp * 16, 0x111111181182ull >> (4 * warp) & 15);
      mbar_init(bar_stat + warp * 16 + 8, 0x111111121811ull >> (4 * warp) & 15);
      mbar_init(bar_chk + 112 + (warp & 7) * 8, 1);
      asm volatile("fence.mbarrier_init.release.cluster;" ::: "memory");
    }
    __syncthreads();
    asm volatile("barrier.cluster.arrive.relaxed.aligned;" ::: "memory");
  }

  if (cta < 0) {
    LOAD_EPOCH();
    const uint32_t buf = sbase + warp * SLOT, bar = sbase + OFF_BAR + warp * 16;
    const uint32_t lsw = (lane & 7) << 4, lhi = (lane >> 4) << 4, lrow = (lane & 15) * 128;
    const bool el = elect_one();
    if (el) {
      mbar_init(bar, 1); mbar_init(bar + 8, 1);
      asm volatile("fence.mbarrier_init.release.cluster;" ::: "memory");
    }
#pragma unroll 1
    for (int rd = 0; rd < (NLAYERS > 1 ? 5 : 2); rd++) {
      if (rd >= 2 && warp >= 8) break;
      const int tk = rd < 2 ? aux * 12 + warp : aux * 8 + warp;
      const int half = tk & 1;
      const int blk = rd < 2 ? (tk >> 1) * 2 + rd : (4 - rd) * 16 + (tk >> 1);
      const CUtensorMap* tm = rd < 2 ? &tm_wqA : (rd == 2 ? &tm_wqB : &tm_wf);
      const int j0 = (blk & 15) >> 1;
#define AUX_LOAD(n) { const uint32_t d_ = buf + ((n) & 1) * 8192, b_ = bar + ((n) & 1) * 8; const int r_ = kslice(j0, 2 * (n) + half) * 64; \
        mbar_expect_tx(b_, 8192); tma_load_2d(d_, tm, b_, blk * 64, r_); tma_load_2d(d_ + 4096, tm, b_, blk * 64, r_ + 32); }
      if (el) {
        if (rd == 3) { wait_flag(&g_flags.wfready[j0].v, ep1 * 16); fence_proxy_async_global(); }
        AUX_LOAD(0); AUX_LOAD(1);
      }
      __syncwarp();
      float cs[8][4];
#pragma unroll
      for (int i = 0; i < 8; i++) cs[i][0] = cs[i][1] = cs[i][2] = cs[i][3] = 0.f;
#pragma unroll 1
      for (int n = 0; n < 8; n++) {
        const uint32_t tb = buf + (n & 1) * 8192 + lrow;
        mbar_wait(bar + (n & 1) * 8, (n >> 1) & 1);
#pragma unroll
        for (int i = 0; i < 16; i++) {
          uint32_t b0, b1, b2, b3;
          ldsm_x4_t(tb + (i >> 2) * 2048 + (((i & 3) * 32 + lhi) ^ lsw), b0, b1, b2, b3);
          mma_bf16(cs[2 * (i & 3)], 0x3F803F80u, 0x3F803F80u, 0x3F803F80u, 0x3F803F80u, b0, b1);
          mma_bf16(cs[2 * (i & 3) + 1], 0x3F803F80u, 0x3F803F80u, 0x3F803F80u, 0x3F803F80u, b2, b3);
        }
        __syncwarp();
        if (el && n < 6) AUX_LOAD(n + 2);
        __syncwarp();
      }
      if (lane < 4) {
#pragma unroll
        for (int i = 0; i < 8; i++) st_b64(&g_colsum[rd >= 2][blk * 32 + i * 4 + lane][half], __float_as_uint(cs[i][0]), (__float_as_uint(cs[i][1]) & ~3u) | (ep1 & 3));
      }
      __syncwarp();
    }
  } else if (warp >= 8) {
    asm volatile("setmaxnreg.dec.sync.aligned.u32 40;");
    if (warp == 8) {
      const bool el = elect_one();
      cluster_wait();
      if (el) {
#pragma unroll 1
        for (int l = 0; l < NLAYERS; l++) {
          const uint32_t par = l & 1;
          const CUtensorMap* tqk = par ? &tm_wf : &tm_wqA;
          const CUtensorMap* tv = par ? &tm_wqB : &tm_wqA;
          const CUtensorMap* two = par ? &tm_woB : &tm_woA;
          if (l == 1) { LOAD_EPOCH(); wait_flag(&g_flags.wfready[jj].v, ep1 * 16); fence_proxy_async_global(); }
#pragma unroll 1
          for (int u = l ? 0 : EARLY; u < 32; u++) {
            if (u >= 4) mbar_wait_sl(bar_done + (u - 4) * 8, par);
            else if (l) mbar_wait_sl(bar_done + (43 + u + (u >> 1)) * 8, par ^ 1);
            else if (u == 1) __nanosleep(STAG1);
            else if (u == 2 && !W23) mbar_wait_sl(bar_full, 0);
            const uint32_t fb = bar_full + u * 8;
            const bool res = u < 4 ? (l || u >= 2) : (u < 11 || (u >= 18 && u < 22));
            mbar_expect_tx(fb, res ? QST : QST + SLOT);
            const int row = kslice(jj, u < 4 ? u & 1 : (u < 18 ? u - 2 : (u < 22 ? u - 6 : u - 20))) * 64 + (int)rank * 32;
            const int ps = u < 4 ? u >> 1 : (u >= 18), col = jj * 128 + ps * 64;
            const int c0 = par ? jj * 128 + (ps ? 0 : 1024) : col;
            const uint32_t dst = sbase + (u & 3) * QST + rank * 4096;
            tma_load_2d_mc(dst, tqk, fb, c0, row);
            tma_load_2d_mc(dst + 8192, tqk, fb, c0 + (par ? 64 : 1024), row);
            tma_load_2d_mc(dst + 16384, tv, fb, col + 2048, row);
            if (l == PRL && u >= PRU && u < PRU + 4) PROFT(473 + u - PRU);
          }
#pragma unroll 1
          for (int s = 0; s < 16; s++) {
            if (s < 5) { if (s != 2 && s != 4) mbar_wait_sl(bar_done + (28 + s) * 8, par); }
            else if (s != 14) mbar_wait_sl(bar_done + (27 + s - (s == 15)) * 8, par);
            const uint32_t fb = bar_full + (32 + s) * 8;
            mbar_expect_tx(fb, SLOT);
            tma_load_2d_mc(sbase + rank * 8192 + (uint32_t)((WO_BSLOT >> (4 * s)) & 15) * SLOT, two, fb, jj * 128 + (int)rank * 64, wslice(jj, s) * 64);
            const int ts = s + par;
            if (s >= 5 && ts < 8) {
              mbar_expect_tx(bar_chk - 8 + ts * 8, SLOT);
              tma_load_2d(sbase + (uint32_t)((WO_ASLOT(par) >> (4 * ts)) & 15) * SLOT, &tm_o, bar_chk - 8 + ts * 8, wslice(jj, ts) * 64, mm * 128);
            }
          }
        }
      }
      __syncwarp();
    } else if (warp == 9) {
      const bool el = elect_one();
      if (el) {
        if (!EARLY) { PROFT(472); tma_load_2d(sbase + OFF_S, &tm_x0, bar_full, jj * 128, mm * 128); }
        if (EARLY < 2) { __nanosleep(STAG1); tma_load_2d(sbase + OFF_S + SLOT, &tm_x0, bar_full + 8, jj * 128 + 64, mm * 128); }
      }
      __syncwarp();
      LOAD_EPOCH();
#pragma unroll 1
      for (int lp = 0; lp < 4 * NLAYERS; lp++) {
        const int l = lp >> 2, ph = lp & 3;
        if (ph == 3) continue;
        const uint32_t par = l & 1;
        const __nv_bfloat16* pb = g_obuf + (ph >> 1) * 64 + (size_t)(mm * 128 + (ph ? 0 : S_LEN) + (lane & 7) * 16 + (jj & 1) * 8) * D_MODEL + (jj >> 1) * 16;
        const CUtensorMap* tm = lp ? &tm_o : &tm_x0;
        const int row = mm * 128 + ((ph || !l) ? 0 : S_LEN);
        const uint32_t bit = ph ? O_BIT(l) : X_BIT(l - 1);
        const uint32_t slots = ph ? (uint32_t)(WO_ASLOT(par) >> (ph * 32 - 28)) : 0x8769876u;
        const unsigned long long fr = ph == 0 ? XPACE : ph == 1 ? (par ? 0x353535351Full : 0x35351F1Eull) : (par ? 0x27262524232232ull : 0x27262524233232ull);
        uint32_t rdy = (lp == 0 || (lp & 7) == 1) ? 0xFF : 0;
        if (lp || !AX) mbar_wait_sl(ph ? bar_done + ((uint32_t)fr & 63) * 8 : (l ? bar_done + 47 * 8 : bar_full), ph ? par : (l ? par ^ 1 : 0));
#pragma unroll 1
        for (int i = 0; i < (ph == 1 ? 4 + par : 7); i++) {
          if (!((rdy >> i) & 1) && (i < NPOLL || ph == 1)) {
            const unsigned* pp = reinterpret_cast<const unsigned*>(pb + srcb(jj, i + ((lane >> 3) & (POLLW - 1))) * 128);
            if (i == 0) __nanosleep(POLL0);
            unsigned v0 = ld_relaxed(pp);
            __nanosleep(POLLGAP);
            unsigned v1 = ld_relaxed(pp);
            uint32_t no;
#pragma unroll 1
            for (int it = 0; it < (1 << 18); it++) {
              no = __ballot_sync(0xffffffffu, (v0 ^ bit) & 1);
              if (!(no & 0xFF)) break;
              v0 = ld_relaxed(pp);
              no = __ballot_sync(0xffffffffu, (v1 ^ bit) & 1);
              if (!(no & 0xFF)) break;
              v1 = ld_relaxed(pp);
            }
            rdy = ((1 | (no & 0xFF00 ? 0 : 2) | (no & 0xFF0000 ? 0 : 4) | (no >> 24 ? 0 : 8)) & ((1 << POLLW) - 1)) << i;
          }
          if (ph || i >= XP0) mbar_wait_sl(bar_done + ((uint32_t)(fr >> (8 * i)) & 63) * 8, par);
          if (el) {
            if (i == 0) PROFT(320 + l * 16 + ph);
            const uint32_t cb = bar_chk + (ph >> 1) * 112 + i * 8;
            mbar_expect_tx(cb, SLOT);
            tma_load_2d(sbase + ((slots >> (4 * i)) & 15) * SLOT, tm, cb, srcb(jj, i) * 128 + (ph >> 1) * 64, row);
          }
          __syncwarp();
        }
        if (ph == 0 && el) {
          if (l) { wait_flag(&g_flags.xready[l][mm].v, ep1 * 8); fence_proxy_async_global(); }
#pragma unroll 1
          for (int u = 11; u < 34; u++) {
            if (u == 18) u = 22;
            mbar_wait_sl(bar_done + (u - 4) * 8, par);
            if (u == 32) mbar_expect_tx(bar_xr, 2 * SLOT);
            tma_load_2d(sbase + OFF_RA + (u & 3) * SLOT, tm, u < 32 ? bar_full + u * 8 : bar_xr, kslice(jj, u < 18 ? u - 2 : (u < 32 ? u - 20 : u - 32)) * 64, row);
          }
        }
        __syncwarp();
      }
      cluster_wait();
    } else {
      const int hw = warp - 10;
      LOAD_EPOCH();
      const bool el = elect_one();
      cluster_wait();
      if (hw == 0) {
        mbar_wait_sl(bar_full + 8, 0);
        if (lane < 7) prefetch_tmap(lane == 0 ? &tm_os : lane == 1 ? &tm_o : lane == 2 ? &tm_wf : lane == 3 ? &tm_wqB : lane == 4 ? &tm_woA : lane == 5 ? &tm_woB : &tm_phi);
#pragma unroll 1
        for (int i = 0; i < (NLAYERS > 1 ? 9 : 0); i++) {
          if (i == 0 || i == 5) mbar_wait_sl(bar_done + (i >> 1) * 12, 0);
          if (el) {
            if (i == 0) { mbar_expect_tx(bar_phi, 2 * SLOT + 8192); tma_load_2d(sbase + OFF_PHI, &tm_phi, bar_phi, 0, jj * 128); }
            else tma_load_2d(sbase + (i > 4 ? 10 : 12) * SLOT - 4096 + i * 4096, &tm_wqB, bar_phi, (i > 4 ? 896 : 0) + jj * 128 + ((i - 1) >> 1) * 64, mm * 64 + (~i & 1) * 32);
          }
          __syncwarp();
          __nanosleep(PFGAP);
        }
      } else {
#pragma unroll 1
        for (int b = 0; b < 2; b++) {
          float4* z = reinterpret_cast<float4*>(g_kv[b] + (jj * 4) * KVH + mm * (4 * KVH / 16)) + lane;
#pragma unroll
          for (int i = 0; i < 6; i++) z[i * 32] = make_float4(0.f, 0.f, 0.f, 0.f);
        }
#pragma unroll 1
        for (int i = 0; i < 16; i++) {
          const int b = i >> 2;
          const uint32_t v = (b == 0 ? O_BIT(0) : b == 1 ? X_BIT(0) : H_BIT(0)) + 1;
          uint4* p = b < 2 ? reinterpret_cast<uint4*>(g_obuf + (size_t)(b * S_LEN + mm * 128 + (i & 3) * 32 + (lane >> 3) * 8) * D_MODEL + jj * 128 + (b ? 0 : 64)) + (lane & 7)
                           : g_halo + (size_t)(mm * 8 + jj) * 512 + i * 32 + lane;
          *p = make_uint4(v, v, v, v);
        }
        fence_proxy_async_global();
      }
      __syncwarp();
      uint32_t chkp = 0;
#pragma unroll 1
      for (int lp = 0; lp < 4 * NLAYERS; lp++) {
        const int l = lp >> 2, ph = (lp & 3) == 2 ? 2 - hw : (lp & 3);
        const uint32_t par = l & 1;
        int lane; asm volatile("mov.u32 %0, %%laneid;" : "=r"(lane));
        if ((lp & 3) == 2 || (hw && ph == 0)) {
          const uint32_t bit = ph ? O_BIT(l) : X_BIT(l - 1);
          uint32_t slots = ph ? (uint32_t)(WO_ASLOT(par) >> (ph * 32 - 28)) : 0x8769876u;
          const uint32_t a0 = sbase + (lane & 7) * 132 + (lane >> 3) * 32;
#pragma unroll 1
          for (int c = 0; c < 7; c++, slots >>= 4) {
            const uint32_t cb = bar_chk + 112 - hw * 112 + c * 8;
#pragma unroll 1
            for (int it = 0; it < (1 << 12); it++) {
              mbar_wait_sl(cb, (chkp >> c) & 1);
              chkp ^= 1u << c;
              if (el && c == 0) PROFT(ph == 1 ? 480 + l * 2 : 488 + l * 2 + (ph >> 1));
              if (lp == 0) break;
              uint32_t bad;
              asm volatile("{\n.reg .b32 w<16>;\n"
                           "ld.shared.u32 w0, [%1 + 0];\n"
                           "ld.shared.u32 w1, [%1 + 1024];\n"
                           "ld.shared.u32 w2, [%1 + 2048];\n"
                           "ld.shared.u32 w3, [%1 + 3072];\n"
                           "ld.shared.u32 w4, [%1 + 4096];\n"
                           "ld.shared.u32 w5, [%1 + 5120];\n"
                           "ld.shared.u32 w6, [%1 + 6144];\n"
                           "ld.shared.u32 w7, [%1 + 7168];\n"
                           "ld.shared.u32 w8, [%1 + 8192];\n"
                           "ld.shared.u32 w9, [%1 + 9216];\n"
                           "ld.shared.u32 w10, [%1 + 10240];\n"
                           "ld.shared.u32 w11, [%1 + 11264];\n"
                           "ld.shared.u32 w12, [%1 + 12288];\n"
                           "ld.shared.u32 w13, [%1 + 13312];\n"
                           "ld.shared.u32 w14, [%1 + 14336];\n"
                           "ld.shared.u32 w15, [%1 + 15360];\n"
                           "lop3.b32 w0, w0, w1, %2, 0x7E;\n"
                           "lop3.b32 w2, w2, w3, %2, 0x7E;\n"
                           "lop3.b32 w4, w4, w5, %2, 0x7E;\n"
                           "lop3.b32 w6, w6, w7, %2, 0x7E;\n"
                           "lop3.b32 w8, w8, w9, %2, 0x7E;\n"
                           "lop3.b32 w10, w10, w11, %2, 0x7E;\n"
                           "lop3.b32 w12, w12, w13, %2, 0x7E;\n"
                           "lop3.b32 w14, w14, w15, %2, 0x7E;\n"
                           "lop3.b32 w0, w0, w2, w4, 0xFE;\nlop3.b32 w6, w6, w8, w10, 0xFE;\nlop3.b32 w0, w0, w12, w14, 0xFE;\nlop3.b32 %0, w0, w6, 1, 0xA8;\n}\n"
                           : "=r"(bad) : "r"(a0 + (slots & 15) * SLOT), "r"(bit) : "memory");
              if (__all_sync(0xffffffffu, bad == 0)) break;
              if (el) {
                fence_proxy_async_smem();
                mbar_expect_tx(cb, SLOT);
                tma_load_2d(sbase + (slots & 15) * SLOT, &tm_o, cb, srcb(jj, c) * 128 + (ph >> 1) * 64, mm * 128 + (ph ? 0 : S_LEN));
                RETRY_COUNT();
              }
              __syncwarp();
            }
            if (el) { mbar_arrive_local(bar_full + (c + (ph ? 25 + ph * 8 : 4)) * 8); if (lp == PRL * 4 && c == 0) PROFT(477); }
            __syncwarp();
          }
          if (ph) continue;
#pragma unroll 1
          for (int hp = 0; hp < 2; hp++) {
            const uint4* src = reinterpret_cast<const uint4*>(g_colsum[par][jj * 64 + hp * 32 + lane]);
            uint32_t bad;
            int it = 0;
            float c[6];
            do {
              bad = 0;
#pragma unroll
              for (int p = 0; p < 3; p++) {
                const uint4 v = ld_ll(src + ((par && p < 2) ? (hp ? -32 : 512) + p * 32 : p * 512));
                bad |= (v.y ^ ep1) | (v.w ^ ep1);
                c[2 * p] = __uint_as_float(v.x) + __uint_as_float(v.z); c[2 * p + 1] = __uint_as_float(v.y) + __uint_as_float(v.w);
              }
              bad &= 3;
              if (bad) __nanosleep(300);
            } while (bad && ++it < (1 << 16));
#pragma unroll
            for (int p = 0; p < 6; p++) {
              uint32_t h, m, lo;
              split3(c[p], h, m, lo);
              sts128(sbase + OFF_LNB + hp * 4096 + (p >> 1) * 1024 + lane * 32 + (p & 1) * 16, h | (m << 16), h | (lo << 16), h | (m << 16), lo | (m << 16));
            }
            fence_proxy_async_smem();
            __syncwarp();
            if (el) { mbar_arrive_local(hp ? bar_stat2 : bar_stat); if (hp == 0) PROFT(324 + l * 16); }
            __syncwarp();
          }
          continue;
        } else if (ph == 0) {
          mbar_wait_sl(bar_done + 24, par);
          const uint4* sp = reinterpret_cast<const uint4*>(g_stats + (size_t)(mm * 128) * 8) + lane;
#pragma unroll 1
          for (int hf = 0; hf < 4; hf++) {
            uint4 v[4];
            uint32_t bad;
            int it = 0;
            do {
              bad = 0;
#pragma unroll
              for (int i = 0; i < 4; i++) { v[i] = ld_ll(sp + (hf * 4 + i) * 32); bad |= (v[i].y ^ STAT_TAG(l)) | (v[i].w ^ STAT_TAG(l)); }
              bad &= 3;
              if (bad) __nanosleep(200);
            } while (bad && ++it < (1 << 16));
            __syncwarp();
            float mean = 0.f, m2 = 0.f;
#pragma unroll
            for (int i = 0; i < 4; i++) {
              float a = __uint_as_float(v[i].x) + __uint_as_float(v[i].z);
              a += __shfl_xor_sync(0xffffffffu, a, 1); a += __shfl_xor_sync(0xffffffffu, a, 2);
              a *= 0.125f;
              const float e0 = __uint_as_float(v[i].x) - a, e1 = __uint_as_float(v[i].z) - a;
              float q = fmaf(fmaf(e0, e0, e1 * e1), 128.f, __uint_as_float(v[i].y) + __uint_as_float(v[i].w));
              q += __shfl_xor_sync(0xffffffffu, q, 1); q += __shfl_xor_sync(0xffffffffu, q, 2);
              if ((lane & 3) == i) { mean = a; m2 = q; }
            }
            const uint32_t row = hf * 32 + (lane & 3) * 8 + (lane >> 2);
            uint32_t h, m, lo;
            split3(-0.5f * mean, h, m, lo);
            sts128(sbase + OFF_LNA + row * 16, h | (h << 16), m | (h << 16), lo | (m << 16), m | (lo << 16));
            sts32f(sbase + OFF_ST + row * 4, rsqrtf(m2 * (1.f / 1024.f) + 1e-5f));
          }
          fence_proxy_async_smem();
          __syncwarp();
          if (el) { mbar_arrive_local(bar_stat); PROFT(323 + l * 16); }
          __syncwarp();
#pragma unroll 1
          for (int i = 0; i < 8 - 4 * l; i++) {
            asm volatile("prefetch.global.L2 [%0];" :: "l"(i < 4 ? (l ? prm.wB_o : prm.wA_o) + (size_t)cta * 8192 + i * 2048 + lane * 64
                                                                 : prm.wB_qkv + (size_t)(cta * 8 + (i - 4) * 2 + (lane >> 4)) * 3072 + 2048 + (lane & 15) * 64));
            __nanosleep(PFGAP);
          }
          continue;
        }
        if (ph == 1) {
          if (par) continue;
#pragma unroll 1
          for (int i = 0; i < 2; i++) {
            if (i && lp + hw == 1 && NLAYERS > 1) {
#pragma unroll 1
              for (int c = 0; c < 8; c++) {
                if (!(c & 3)) asm volatile("bar.sync %0, 288;" :: "r"(BAR_WF + (c >> 2)) : "memory");
                if (el) {
                  tma_store_2d(&tm_wf, sbase + 11 * SLOT + c * 4096, (c < 4 ? 1024 : -128) + jj * 128 + (c >> 1) * 64, mm * 64 + (c & 1) * 32);
                  if ((c & 3) == 3) {
                    asm volatile("cp.async.bulk.commit_group;\ncp.async.bulk.wait_group.read 0;" ::: "memory");
                    mbar_arrive_local(bar_phi + (c >> 2) * 8);
                  } else __nanosleep(WFGAP);
                }
                __syncwarp();
              }
              if (el) { bulk_commit_wait(); signal_release(&g_flags.wfready[jj].v); PROFT(335); }
              __syncwarp();
            }
            mbar_wait_sl(bar_done + (i ? HW1 : (hw ? 19 : HW0)) * 8, 0);
            if (lp + hw == 2 && NLAYERS > 1) mbar_wait_sl(bar_phi, 1);
            const uint4* src = g_halo + (size_t)(mm * 8 + jj - 8) * 512 + i * 256 + hw * 128 + lane;
            uint4 v[4];
            int it = 0;
            bool ok;
            do {
#pragma unroll
              for (int j = 0; j < 4; j++) v[j] = mm ? ld_b128(src + j * 32) : make_uint4(H_BIT(l), 0, 0, 0);
              ok = __all_sync(0xffffffffu, (((v[0].x ^ H_BIT(l)) | (v[1].x ^ H_BIT(l)) | (v[2].x ^ H_BIT(l)) | (v[3].x ^ H_BIT(l))) & 1) == 0);
            } while (!ok && ++it < (1 << 16));
#pragma unroll
            for (int j = 0; j < 4; j++) sts128(sbase + OFF_S + hw * SLOT + j * 512 + lane * 16, v[j].x, v[j].y, v[j].z, v[j].w);
            __syncwarp();
            if (el) { mbar_arrive_local(bar_halo + hw * 8); PROFT(331 + l * 16 + i * 2 + hw); }
            __syncwarp();
          }
        } else if (hw == 0 && l < NLAYERS - 1) {
          bar_sync<BAR_X1, 288>();
          if (el) {
            PROFT(328 + l * 16);
            mbar_wait_sl(bar_full + XD * 8, par ^ 1);
            tma_store_2d(&tm_o, sbase + 11 * SLOT, jj * 128 + 64, mm * 128 + S_LEN);
            bulk_commit_wait();
            signal_release(&g_flags.xready[l + 1][mm].v);
            PROFT(330 + l * 16);
          }
          __syncwarp();
        }
      }
    }
    cluster_sync();
  } else {
    asm volatile("setmaxnreg.inc.sync.aligned.u32 232;");
    LOAD_EPOCH();
    const int wg = warp >> 2;
    const int r0 = warp * 16;
    const uint32_t pK = sbase + OFF_S, pV = sbase + OFF_S + SLOT;
#define PMASKS(on, bit) const uint32_t pm0 = ((on) && t == (g & 3) && (g >> 2) == (g & 1)), pm1 = ((on) && t == (g & 3) && (g >> 2) != (g & 1)), pbit = (bit)
#define PBIT0(w) (((w) & ~pm0) | (pbit & pm0))
#define PBIT1(w) (((w) & ~pm1) | (pbit & pm1))
#define LANE_CONSTS() \
    int lane; asm volatile("mov.u32 %0, %%laneid;" : "=r"(lane)); \
    const int g = lane >> 2, t = lane & 3; \
    const uint32_t srowoff = (r0 + (lane & 15)) * 128, lsw = (lane & 7) << 4, lhi = (lane >> 4) << 4, lsw2 = (lane & 6) << 3; \
    (void)g; (void)t; (void)srowoff; (void)lsw; (void)lhi; (void)lsw2;
    uint32_t stgp = 0, peer;
    asm volatile("mapa.shared::cluster.u32 %0, %1, %2;" : "=r"(peer) : "r"(sbase), "r"(rank ^ 1));
    peer -= sbase;
    const uint32_t dA0 = (((sbase & 0x3FFFF) + wg * 8192) >> 4) | 0x10000u, dB0 = ((sbase & 0x3FFFF) >> 4) | 0x2000000u;
    cluster_wait();
#define DESC(lo, hi) ((uint64_t)(uint32_t)(lo) | ((uint64_t)(hi) << 32))
#define STG_ARRIVE() { __syncwarp(); if (elect_one()) mbar_arrive_local(bar_stg); }
#define STG_WAIT() { mbar_wait(bar_stg, stgp); stgp ^= 1; }
#define PROFS() do {} while (0)
#define REL(addr) { if (elect_one()) { mbar_arrive_local(addr); asm volatile("mbarrier.arrive.shared::cluster.b64 _, [%0];" :: "r"((addr) + peer) : "memory"); } }
#define QSTEP(ACC, DA, SC, PRE) { \
      const uint32_t da = (DA), db = dB0 + (ub & 0x18) * (QST >> 7); \
      mbar_wait(ub, par); \
      PRE; \
      wgmma_fence(); \
      wgmma4_n192<SC>(ACC, da, db); \
      wgmma_commit(); PROFS(); }
#define QREL() { wgmma_wait<1>(); REL(ub + 376); ub += 8; }
#define RA_CUR (dA0 + (OFF_RA >> 4) + (ub & 0x18) * (SLOT >> 7))
#define PUMP1() { QSTEP(S1, RA_CUR, 1, {}); QREL(); }
#define PUMP0() { PUMP1(); SCHED_FENCE(); }
#define PUMP() if (h == 0) PUMP1()
#define WSTEP() { \
      const uint32_t s4 = (ub - bar_full - 256) >> 1; \
      const uint32_t da = dA0 + (((uint32_t)(WO_ASLOT(par) >> s4) & 15) << 10), db = dB0 + (((uint32_t)(WO_BSLOT >> s4) & 15) << 10); \
      mbar_wait(ub, par); \
      wgmma_fence(); \
      wgmma4_n128<1>(S1, da, db); \
      wgmma_commit(); PROFS(); \
      wgmma_wait<1>(); \
      if (s4) REL(ub + 376); \
      ub += 8; }
#define PUMPS(n) { _Pragma("unroll 1") for (int i_ = 0; i_ < (n); i_++) PUMP1(); }
#define SITE(n) { if ((BMASK >> (n)) & 1) PUMP1(); SCHED_FENCE(); }
#define LNSTEP(ACC, hh) { wgmma_fence(); wgmma_n192<1, 0>(ACC, make_desc(sbase + OFF_LNA + wg * 1024, 0, 128) ^ (1ull << 62), make_desc(sbase + OFF_LNB + (hh) * 4096, 0, 128) ^ (1ull << 62)); }
#define DRAIN_B(ACC) { \
      LANE_CONSTS(); \
      STAGE_V(ACC + 64, pV); \
      _Pragma("unroll") for (int i_ = 0; i_ < 64; i_++) st[i_] = ACC[i_]; \
      PIN(st, 64); }
#define WARP_STORE(tm, tile, col, row) { fence_proxy_async_smem(); __syncwarp(); \
      if (elect_one()) { tma_store_2d(tm, (tile) + r0 * 128, col, (row) + r0); asm volatile("cp.async.bulk.commit_group;" ::: "memory"); } __syncwarp(); }
#define PUBLISH_O() WARP_STORE(&tm_os, pO, jj * 128 + h * 64, mm * 128)
#define X_OUT(pc, on) { \
      PMASKS(on, X_BIT(l)); \
      _Pragma("unroll") for (int j = (pc) * 4; j < (pc) * 4 + 4; j++) \
        stsm_x4(pK + (pc) * SLOT + srowoff + ((((uint32_t)(j & 3) << 5) + lhi) ^ lsw), \
                PBIT0(pack_bf16(S1[j * 8 + 0], S1[j * 8 + 1])), PBIT0(pack_bf16(S1[j * 8 + 2], S1[j * 8 + 3])), \
                PBIT1(pack_bf16(S1[j * 8 + 4], S1[j * 8 + 5])), PBIT1(pack_bf16(S1[j * 8 + 6], S1[j * 8 + 7]))); }
#define REST_P1(SKEW) { \
      mbar_wait(bar_stat2, par); \
      LNSTEP(S1, 1); \
      _Pragma("unroll 1") while (ub < bar_full + 256) { \
        if (ub == bar_full + 256 - 8 * (SKEW) && wg == 0) bar_sync<BAR_SKEW, 256>(); \
        QSTEP(S1, RA_CUR, 1, {}); \
        if (ub == bar_full + 248 && wg == 1) bar_arrive<BAR_SKEW, 256>(); \
        QREL(); \
      } \
      mbar_wait(bar_done + (31 - (SKEW)) * 8, par);        \
      wgmma_wait<0>(); \
      ACC_FENCE(S1, 96); \
      REL(bar_done + 31 * 8); \
      PROF(13); }
#define FOLD(tile, rd) { \
          LANE_CONSTS(); \
          float d[32]; \
          ACC_DEF(d, 32); \
          mbar_wait(bar_phi, 0); \
          wgmma_fence(); \
          _Pragma("unroll") for (int i = 0; i < 2; i++) { \
            const uint64_t da = make_desc((tile) + wg * 8192 + i * 64, 16, 1024); \
            const uint64_t db = make_desc(sbase + OFF_PHI + wg * 4096 + i * 2048, 16, 512) ^ (3ull << 62); \
            wgmma_n32<0>(d + i * 16, da, db); wgmma_n32<1>(d + i * 16, da + 2, db + 64); \
          } \
          wgmma_commit(); \
          PUMP0(); \
          ACC_FENCE(d, 32); \
          bar_wg(wg); \
          _Pragma("unroll") for (int i = 0; i < 4; i++) { \
            const float* x = d + (i & 1) * 8 + (i >> 1) * 2; \
            if (rd) sts128((tile) + wg * 8192 + ((warp & 3) * 16 + (i >> 1) * 8 + g) * 128 + (((2 * t + (i & 1)) ^ g) << 4), \
                           pack_bf16(x[0], x[1]), pack_bf16(x[4], x[5]), pack_bf16(x[16], x[17]), pack_bf16(x[20], x[21])); \
            else stsm_x4((tile) + srowoff + ((((uint32_t)i << 5) + lhi) ^ lsw), pack_bf16(d[i * 8], d[i * 8 + 1]), pack_bf16(d[i * 8 + 2], d[i * 8 + 3]), \
                         pack_bf16(d[i * 8 + 4], d[i * 8 + 5]), pack_bf16(d[i * 8 + 6], d[i * 8 + 7])); \
          } \
          }
#define LOAD_X0(base) \
      _Pragma("unroll") for (int j = 0; j < 8; j++) { \
        uint32_t x0, x1, x2, x3; \
        ldsm_x4((base) + (j >> 2) * SLOT + srowoff + ((((uint32_t)(j & 3) << 5) + lhi) ^ lsw), x0, x1, x2, x3); \
        S1[j * 8 + 0] = bf_lo(x0); S1[j * 8 + 1] = bf_hi(x0); S1[j * 8 + 2] = bf_lo(x1); S1[j * 8 + 3] = bf_hi(x1); \
        S1[j * 8 + 4] = bf_lo(x2); S1[j * 8 + 5] = bf_hi(x2); S1[j * 8 + 6] = bf_lo(x3); S1[j * 8 + 7] = bf_hi(x3); \
      }
#define LOAD_X() { \
      wgmma_wait<0>(); \
      mbar_wait(bar_xr, par); \
      LOAD_X0(sbase + OFF_RA); \
      ACC_FENCE(S1, 64); \
      __syncwarp(); if (elect_one()) mbar_arrive_local(bar_lx); }

    float S1[96];
#pragma unroll
    for (int i = 0; i < 64; i++) S1[i] = 0.f;
#pragma unroll 1
    for (int l = 0; l < NLAYERS; l++) {
      const uint32_t par = l & 1;
      bar_wg(wg);
      PROF(0);
      uint32_t ub = bar_full;
      float S0[96];
      {
        LANE_CONSTS();
        ACC_DEF(S0, 96);
        QSTEP(S0, dA0 + (OFF_S >> 4), 0, {});
        ub += 8;
        PROF(1);
        if (l == 0) { mbar_wait(ub, 0); LOAD_X0(pK); }
        else { X_OUT(1, false); fence_proxy_async_smem(); }
        SCHED_FENCE();
        {
          float a0 = S1[0], a1 = S1[2], b0 = S1[1], b1 = S1[3];
#pragma unroll
          for (int i = 4; i < 64; i += 4) { a0 += S1[i]; b0 += S1[i + 1]; a1 += S1[i + 2]; b1 += S1[i + 3]; }
          a0 += b0; a1 += b1;
          a0 += __shfl_xor_sync(0xffffffffu, a0, 1); a1 += __shfl_xor_sync(0xffffffffu, a1, 1);
          a0 += __shfl_xor_sync(0xffffffffu, a0, 2); a1 += __shfl_xor_sync(0xffffffffu, a1, 2);
          a0 *= (1.f / 128.f); a1 *= (1.f / 128.f);
          asm volatile("" : "+f"(a0), "+f"(a1));
          bar_wg(wg);
          QSTEP(S0, dA0 + ((OFF_S + SLOT) >> 4), 1, wgmma_wait<0>());
          REL(ub + 376); ub += 8;
          SCHED_FENCE();
          float q0 = 0.f, q1 = 0.f;
          b0 = 0.f; b1 = 0.f;
#pragma unroll
          for (int i = 0; i < 64; i += 4) {
            const float d0 = S1[i] - a0, d1 = S1[i + 1] - a0, d2 = S1[i + 2] - a1, d3 = S1[i + 3] - a1;
            q0 = fmaf(d0, d0, q0); b0 = fmaf(d1, d1, b0); q1 = fmaf(d2, d2, q1); b1 = fmaf(d3, d3, b1);
          }
          q0 += b0; q1 += b1;
          q0 += __shfl_xor_sync(0xffffffffu, q0, 1); q1 += __shfl_xor_sync(0xffffffffu, q1, 1);
          q0 += __shfl_xor_sync(0xffffffffu, q0, 2); q1 += __shfl_xor_sync(0xffffffffu, q1, 2);
          if (t < 2) st_b64(g_stats + (size_t)(mm * 128 + r0 + g + t * 8) * 8 + jj, __float_as_uint(t ? a1 : a0), (__float_as_uint(t ? q1 : q0) & ~3u) | STAT_TAG(l));
        }
        if (l) { asm volatile("cp.async.bulk.wait_group 0;" ::: "memory"); bar_arrive<BAR_X1, 288>(); }
        ACC_DEF(S1, 96);
        QSTEP(S1, dA0 + (OFF_S >> 4), 0, {});
        QREL();
        QSTEP(S1, dA0 + ((OFF_S + SLOT) >> 4), 1, {});
        QREL();
#pragma unroll 1
        for (int i = 0; i < 14; i++) {
          QSTEP(S0, RA_CUR, 1, {});
          if (i == 0) PROF(2);
          QREL();
        }
      }
      LANE_CONSTS();
      mbar_wait(bar_stat, par);
      LNSTEP(S0, 0);
      wgmma_commit();
      const float rs0 = lds32f(sbase + OFF_ST + (r0 + g) * 4), rs1 = lds32f(sbase + OFF_ST + (r0 + g + 8) * 4);
      PUMP0();
      ACC_FENCE(S0, 96);
      PROF(3);
      if (!par) {
        constexpr uint32_t par = 0;
        uint32_t qa[16];
        uint32_t kf[32], vf[32];
#define DRAIN_A(ACC, hp, PMP) { \
          LANE_CONSTS(); \
          FRAG(kf + 16, ACC + 32, 0, (hp) * 2); \
          PMP; \
          FRAG(vf + 16, ACC + 64, 1, (hp) * 2 + 1); \
          _Pragma("unroll") for (int i_ = 0; i_ < 16; i_++) qa[i_] = pack_bf16(ACC[2 * i_], ACC[2 * i_ + 1]); \
          PINU(qa, 16); }
        DRAIN_A(S0, 0, PUMP0());
        if (l == 0 && NLAYERS > 1) {
#pragma unroll 1
          for (int rd = 1; rd >= 0; rd--) {
            FOLD(sbase + (12 - rd) * SLOT, rd);
            fence_proxy_async_smem();
            asm volatile("bar.arrive %0, 288;" :: "r"(BAR_WF + 1 - rd) : "memory");
          }
        }
        PUMPS(FPUMP);
        if (l == 0 && NLAYERS > 1) mbar_wait(bar_phi, 1);
#pragma unroll 1
        for (int h = 0; h < 2; h++) {
          const uint32_t pO = sbase + (h ? 3 : 12) * SLOT;
          PROF(4 + h * 12);
          LANE_CONSTS();
          FRAG_PUT(kf + 16, 10); FRAG_PUT(vf + 16, 11);
          STG_ARRIVE();
          if (h) { LOAD_X(); if (AW0) WSTEP(); } else PUMPS(HPUMP2);
          STG_WAIT();
          if (warp == 0) mbar_wait(bar_halo, h);
          FRAG_GET(kf, 10);
          PROF(5 + h * 12);
          float s[2][4][4];
#pragma unroll
          for (int ks = 0; ks < 2; ks++)
#pragma unroll
            for (int i = 0; i < 8; i++) {
              const int hh = (i >> 1) & 1, jb = (i & 1) + (~i >> 1 & 2);
              const uint32_t* b = kf + (jb >> 1) * 16 + hh * 8 + ks * 4 + (jb & 1) * 2;
              if (ks) mma_bf16(s[hh][jb], qa[hh * 8 + 4], qa[hh * 8 + 5], qa[hh * 8 + 6], qa[hh * 8 + 7], b[0], b[1]);
              else mma_bf16_z(s[hh][jb], qa[hh * 8], qa[hh * 8 + 1], qa[hh * 8 + 2], qa[hh * 8 + 3], b[0], b[1]);
            }
          PUMP();
          PROF(6 + h * 12);
          const bool e = g & 1, hb = (2 * t + (g & 1)) <= g;
          float va[2][2], vb[2][2], mx[2][2];
#pragma unroll
          for (int hh = 0; hh < 2; hh++) {
            va[hh][0] = e ? s[hh][1][1] : s[hh][1][0];
            vb[hh][0] = hb ? (e ? s[hh][2][1] : s[hh][2][0]) : (e ? s[hh][0][1] : s[hh][0][0]);
            va[hh][1] = e ? s[hh][2][3] : s[hh][2][2];
            vb[hh][1] = hb ? (e ? s[hh][3][3] : s[hh][3][2]) : (e ? s[hh][1][3] : s[hh][1][2]);
          }
          if (warp == 0 && mm == 0) {
#pragma unroll
            for (int hh = 0; hh < 2; hh++) { va[hh][0] = -INFINITY; if (!hb) { vb[hh][0] = -INFINITY; vb[hh][1] = -INFINITY; } }
          }
#pragma unroll
          for (int i = 0; i < 4; i++) mx[i >> 1][i & 1] = fmaxf(va[i >> 1][i & 1], vb[i >> 1][i & 1]);
#pragma unroll
          for (int o = 1; o <= 2; o <<= 1)
#pragma unroll
            for (int i = 0; i < 4; i++) mx[i >> 1][i & 1] = fmaxf(mx[i >> 1][i & 1], __shfl_xor_sync(0xffffffffu, mx[i >> 1][i & 1], o));
          const float sc0 = rs0 * (0.17677669529663687f * LOG2E), sc1 = rs1 * (0.17677669529663687f * LOG2E);
#pragma unroll
          for (int i = 0; i < 4; i++) {
            const float sc = (i & 1) ? sc1 : sc0, m = mx[i >> 1][i & 1];
            va[i >> 1][i & 1] = ex2((va[i >> 1][i & 1] - m) * sc); vb[i >> 1][i & 1] = ex2((vb[i >> 1][i & 1] - m) * sc);
            mx[i >> 1][i & 1] = va[i >> 1][i & 1] + vb[i >> 1][i & 1];
          }
          if (h == 0 && ASITE) { PIN(&va[0][0], 4); PIN(&vb[0][0], 4); PIN(&mx[0][0], 4); PUMP1(); }
          if (warp == 0) mbar_wait(bar_halo + 8, h);
          FRAG_GET(vf, 11);
#pragma unroll
          for (int o = 1; o <= 2; o <<= 1)
#pragma unroll
            for (int i = 0; i < 4; i++) mx[i >> 1][i & 1] += __shfl_xor_sync(0xffffffffu, mx[i >> 1][i & 1], o);
          const uint32_t selA = e ? 0x1044 : 0x4410, selB = e ? 0x3244 : 0x4432, selL = hb ? 0x4444 : selB, selH = hb ? selB : 0x4444;
          float o[2][4][4];
          uint32_t pa[2][8];
#pragma unroll
          for (int hh = 0; hh < 2; hh++) {
            const float i0 = rcp_fast(mx[hh][0]), i1 = rcp_fast(mx[hh][1]);
            const uint32_t w0 = pack_bf16(va[hh][0] * i0, vb[hh][0] * i0), w1 = pack_bf16(va[hh][1] * i1, vb[hh][1] * i1);
            pa[hh][0] = __byte_perm(w0, 0, selL); pa[hh][2] = __byte_perm(w0, 0, selA); pa[hh][3] = __byte_perm(w1, 0, selL);
            pa[hh][4] = __byte_perm(w0, 0, selH); pa[hh][5] = __byte_perm(w1, 0, selA); pa[hh][7] = __byte_perm(w1, 0, selH);
            pa[hh][1] = pa[hh][0] & pa[hh][4]; pa[hh][6] = pa[hh][3] & pa[hh][7];
          }
          PROF(7 + h * 12);
#pragma unroll
          for (int i = 0; i < 8; i++) mma_bf16_z(o[i >> 2][i & 3], pa[i >> 2][4], pa[i >> 2][5], pa[i >> 2][6], pa[i >> 2][7], vf[16 + 2 * i], vf[17 + 2 * i]);
#pragma unroll
          for (int i = 0; i < 8; i++) mma_bf16(o[i >> 2][i & 3], pa[i >> 2][0], pa[i >> 2][1], pa[i >> 2][2], pa[i >> 2][3], vf[2 * i], vf[2 * i + 1]);
          if (h == 0) PUMP1() else mbar_wait(bar_done + 30 * 8, par);
          if (NLAYERS > 1) mbar_wait(bar_phi + 8, 0);
#pragma unroll
          for (int i = 0; i < 4; i++) {
            const int hh = i >> 1, dp = i & 1;
            PMASKS(true, O_BIT(l));
            stsm_x4(pO + srowoff + ((hh * 64 + dp * 32 + lhi) ^ lsw), PBIT0(pack_bf16(o[hh][dp * 2][0], o[hh][dp * 2][1])), PBIT0(pack_bf16(o[hh][dp * 2][2], o[hh][dp * 2][3])),
                    PBIT1(pack_bf16(o[hh][dp * 2 + 1][0], o[hh][dp * 2 + 1][1])), PBIT1(pack_bf16(o[hh][dp * 2 + 1][2], o[hh][dp * 2 + 1][3])));
          }
          PUBLISH_O();
          PROF(11 + h * 12);
          if (h) break;
          REST_P1(ASKEW);
          asm volatile("cp.async.bulk.wait_group.read 0;" ::: "memory");
          DRAIN_A(S1, 1, {});
        }
      } else {
        constexpr uint32_t par = 1;
        float st[64];
        DRAIN_B(S0);
        if (warp < 2) sts128(sbase + OFF_ONES + warp * 512 + lane * 16, 0x3F803F80u, 0x3F803F80u, 0x3F803F80u, 0x3F803F80u);
        const float c0 = rs0 * LOG2E, c1 = rs1 * LOG2E;
#define KV_MMA(vs) { \
          const uint32_t dp = dA0 + 12 * 1024 - wg * 2560, dv = dA0 + (vs) * 1024 + ((OFF_ONES - (vs) * SLOT - 16) << 12) - wg * (512 << 16); \
          STG_WAIT(); \
          wgmma_fence(); \
          _Pragma("unroll") for (int ks = 0; ks < 8; ks++) { \
            const uint64_t a = DESC(dp + ks * 128, 0x40000040), b = DESC(dv + ks * (64 - (64 << 16)), 0x80000020); \
            if (ks == 0) wgmma_n40<0, 1>(kv, a, b); else wgmma_n40<1, 1>(kv, a, b); } \
          wgmma_commit(); }
#define KV_RED(hp) { \
          float* kvg = g_kv[l >> 1] + (jj * 4 + (hp) * 2) * KVH + warp * 768 + lane * 4; \
          _Pragma("unroll") for (int i = 0; i < 5; i++) red_v4(kvg + i * 128, kv[i * 3], kv[i * 3 + 1], kv[i * 3 + 2], 1.f); \
          red_v4(kvg + 640, kv[15], kv[16], kv[18], 1.f); }
#define KV_LOAD(hp) { \
          const uint4* kvg = reinterpret_cast<const uint4*>(g_kv[l >> 1] + (jj * 4 + (hp) * 2) * KVH) + warp * 192 + lane; \
          _Pragma("unroll") for (int i = 0; i < 6; i++) v[i] = ld_b128(kvg + i * 32); }
#define KVV(i) __uint_as_float((i) % 3 == 0 ? v[(i) / 3].x : ((i) % 3 == 1 ? v[(i) / 3].y : v[(i) / 3].z))
#define KV_TILE(hp) { \
          _Pragma("unroll 1") for (int it = 0; it < (1 << 16); it++) { \
            if (__all_sync(0xffffffffu, (v[0].w & v[1].w & v[2].w & v[3].w & v[4].w & v[5].w) == 0x41800000u)) break; \
            RETRY_COUNT(); \
            KV_LOAD(hp); \
          } \
          PROF(25 + (hp)); \
          const uint32_t e = lane & 7, jt = ((lane >> 1) & 4) + (e >> 1); \
          const uint32_t row = ((((warp >> 1) ^ wg) & 1) << 5) + ((jt & 1) << 4) + ((warp & 1) << 3) + (jt & 6) + (e & 1); \
          const uint32_t kd = pV + wg * 8192 + row * 128, ksw = (row & 7) << 4; \
          _Pragma("unroll") for (int i = 0; i < 2; i++) \
            stsm_x4(kd + ((i * 32 + lhi) ^ ksw), pack_bf16(KVV(i * 8), KVV(i * 8 + 1)), pack_bf16(KVV(i * 8 + 2), KVV(i * 8 + 3)), \
                    pack_bf16(KVV(i * 8 + 4), KVV(i * 8 + 5)), pack_bf16(KVV(i * 8 + 6), KVV(i * 8 + 7))); \
          stsm_x4(kd + ((64u + lhi) ^ ksw), pack_bf16(KVV(16), 1.f), pack_bf16(KVV(17), 1.f), 0u, 0u); }
#pragma unroll 1
        for (int h = 0; h < 2; h++) {
          PROF(4 + h * 2);
          SITE(0);
          LANE_CONSTS();
          const uint32_t dsw = (uint32_t)(g ^ (2 * t)) << 4, dst = ((t & 2) ? pK : sbase + 12 * SLOT) + (r0 + g) * 128;
          float e[16], f[16];
          float mn0 = rmin16(st);
          asm volatile("" : "+f"(mn0)); SCHED_FENCE();
          float sa = exps16(e, st, -c0, mn0 * c0), mx0 = rmax16(st);
          asm volatile("" : "+f"(sa), "+f"(mx0)); PIN(e, 16); SITE(1);
          if (h) STG_WAIT();
          store16(e, sa, dst, dsw, 4);
          float sb = exps16(f, st, c0, -mx0 * c0), mn1 = rmin16(st + 2);
          asm volatile("" : "+f"(sb), "+f"(mn1)); PIN(f, 16); SITE(2);
          store16(f, sb, dst, dsw, 0);
          float sc = exps16(e, st + 2, -c1, mn1 * c1), mx1 = rmax16(st + 2);
          asm volatile("" : "+f"(sc), "+f"(mx1)); PIN(e, 16); SITE(3);
          store16(e, sc, dst + 1024, dsw, 4);
          float sd = exps16(f, st + 2, c1, -mx1 * c1);
          asm volatile("" : "+f"(sd)); PIN(f, 16); SITE(4);
          store16(f, sd, dst + 1024, dsw, 0);
          PROF(5 + h * 2);
          if (h) break;
          {
            float kv[20];
            ACC_DEF(kv, 20);
            fence_proxy_async_smem();
            STG_ARRIVE();
            KV_MMA(11);
            PUMP0();
            ACC_FENCE(kv, 20);
            KV_RED(0);
            STG_ARRIVE();
          }
#pragma unroll
          for (int i = 0; i < 32; i++) st[i] = st[32 + i];
        }
        float mq[8];
        uint4 v[6];
        {
          float kv[20];
          if (KT0) { LANE_CONSTS(); KV_LOAD(0); }
          mbar_wait(bar_stat2, par);
          LNSTEP(S1, 1);
          ub = bar_full + 240;
          PUMP1();
          if (wg == 0) bar_sync<BAR_SKEW, 256>();
          QSTEP(S1, RA_CUR, 1, {});
          if (wg == 1) bar_arrive<BAR_SKEW, 256>();
          QREL();
          if (KT0 == 2) { LANE_CONSTS(); KV_TILE(0); }
          mbar_wait(bar_done + 30 * 8, par);
          wgmma_wait<0>();
          ACC_FENCE(S1, 96);
          if (!(RLATE & 2)) REL(bar_done + 31 * 8);
          PROF(13);
          LANE_CONSTS();
          STAGE_V(S1 + 64, sbase + 3 * SLOT);
          fence_proxy_async_smem();
          STG_ARRIVE();
          if (RLATE & 2) REL(bar_done + 31 * 8);
#pragma unroll
          for (int i = 0; i < 32; i++) st[i] = S1[i];
          PIN(st, 32);
          PROF(16);
          ACC_DEF(kv, 20);
          KV_MMA(3);
          SCHED_FENCE();
          if (!KT0) KV_LOAD(0);
          extrema(mq, st, c0, c1);
          PIN(mq, 8);
          SCHED_FENCE();
          wgmma_wait<0>();
          ACC_FENCE(kv, 20);
          KV_RED(1);
          PROF(17);
        }
#pragma unroll 1
        for (int h = 0; h < 2; h++) {
          const uint32_t pO = sbase + (h ? 3 : 8) * SLOT;
          LANE_CONSTS();
          uint32_t fq[32];
          expp16(fq, st, -c0, mq[0], -c1, mq[1]); expp16(fq + 8, st, c0, mq[2], c1, mq[3]); PINU(fq, 16);
          PROF(18 + h * 14);
          SCHED_FENCE();
          if (h) {
            asm volatile("cp.async.bulk.wait_group.read 0;" ::: "memory");
            mbar_wait(bar_lx, par);
          }
          if (h || KT0 < 2) {
            KV_TILE(h);
            fence_proxy_async_smem();
            STG_ARRIVE();
          }
          SCHED_FENCE();
          expp16(fq + 16, st + 16, -c0, mq[4], -c1, mq[5]); PINU(fq + 16, 8);
          if (h || KT0 < 2) STG_WAIT();
          wgmma_wait<0>();
          ACC_FENCE(S1, 64);
          PROF(19 + h * 14);
          float o[4][20];
#define O_MMA(hh) { \
            const uint64_t db = make_desc(pV + (hh) * 8192, 16, 1024); \
            ACC_DEF(o[(hh) * 2], 20); ACC_DEF(o[(hh) * 2 + 1], 20); \
            wgmma_fence(); \
            wgmma_n40_rs<0>(o[(hh) * 2], fq + (hh) * 16, db + 256); wgmma_n40_rs<0>(o[(hh) * 2 + 1], fq + (hh) * 16 + 8, db); \
            wgmma_n40_rs<1>(o[(hh) * 2], fq + (hh) * 16 + 4, db + 384); wgmma_n40_rs<1>(o[(hh) * 2 + 1], fq + (hh) * 16 + 12, db + 128); \
            wgmma_commit(); }
          O_MMA(0);
          SCHED_FENCE();
          expp16(fq + 24, st + 16, c0, mq[6], c1, mq[7]); PINU(fq + 24, 8);
          SCHED_FENCE();
          PMASKS(true, O_BIT(l));
#pragma unroll
          for (int hh = 0; hh < 2; hh++) {
            if (hh && !OW) O_MMA(1);
            wgmma_wait<0>();
            ACC_FENCE(o[hh * 2], 20); ACC_FENCE(o[hh * 2 + 1], 20);
            if (!hh && OW) { O_MMA(1); SCHED_FENCE(); }
            const float* x = o[hh * 2];
            const float* y = o[hh * 2 + 1];
            const float rx0 = rcp_fast(x[17]), ry0 = rcp_fast(y[17]), rx1 = rcp_fast(x[19]), ry1 = rcp_fast(y[19]);
            const float i0 = rcp_fast(fmaf(x[16], rx0, y[16] * ry0) + 1e-6f), i1 = rcp_fast(fmaf(x[18], rx1, y[18] * ry1) + 1e-6f);
            const float ax0 = rx0 * i0, ay0 = ry0 * i0, ax1 = rx1 * i1, ay1 = ry1 * i1;
#pragma unroll
            for (int dp = 0; dp < 2; dp++)
              stsm_x4(pO + srowoff + ((hh * 64 + dp * 32 + lhi) ^ lsw),
                      PBIT0(pack_bf16(fmaf(x[dp * 8], ax0, y[dp * 8] * ay0), fmaf(x[dp * 8 + 1], ax0, y[dp * 8 + 1] * ay0))),
                      PBIT0(pack_bf16(fmaf(x[dp * 8 + 2], ax1, y[dp * 8 + 2] * ay1), fmaf(x[dp * 8 + 3], ax1, y[dp * 8 + 3] * ay1))),
                      PBIT1(pack_bf16(fmaf(x[dp * 8 + 4], ax0, y[dp * 8 + 4] * ay0), fmaf(x[dp * 8 + 5], ax0, y[dp * 8 + 5] * ay0))),
                      PBIT1(pack_bf16(fmaf(x[dp * 8 + 6], ax1, y[dp * 8 + 6] * ay1), fmaf(x[dp * 8 + 7], ax1, y[dp * 8 + 7] * ay1))));
          }
          PUBLISH_O();
          PROF(20 + h * 14);
          if (h) break;
#pragma unroll
          for (int i = 0; i < 32; i++) st[i] = S1[32 + i];
          PIN(st, 32);
          LOAD_X();
          bar_wg(wg);
          WSTEP();
          SCHED_FENCE();
          if (KVL == 0) KV_LOAD(1);
          extrema(mq, st, c0, c1);
          PIN(mq, 8);
          if (KVL == 1) { SCHED_FENCE(); KV_LOAD(1); }
          PROF(31);
        }
      }
      __syncwarp();
      if (elect_one()) mbar_arrive_local(bar_epi);
      bar_wg(wg);
#pragma unroll 1
      while (ub < bar_full + 384) {
        WSTEP();
        if (ub == bar_full + 8 * 41) { asm volatile("cp.async.bulk.wait_group.read 0;" ::: "memory"); PROF(35); }
        if (ub == bar_full + 8 * 42) PROF(36);
      }
      wgmma_wait<0>();
      ACC_FENCE(S1, 64);
      if (!RLATE) REL(bar_done + 47 * 8);
      PROF(37);
      {
        LANE_CONSTS();
        X_OUT(0, l < NLAYERS - 1);
        WARP_STORE(l < NLAYERS - 1 ? &tm_os : &tm_xo, pK, jj * 128, mm * 128 + (l < NLAYERS - 1 ? S_LEN : 0));
        if (RLATE) REL(bar_done + 47 * 8);
        if (l == NLAYERS - 1) {
          X_OUT(1, false);
          WARP_STORE(&tm_xo, pV, jj * 128 + 64, mm * 128);
          asm volatile("cp.async.bulk.wait_group 0;" ::: "memory");
        }
      }
#pragma unroll
      for (int i = 32; i < 64; i++) { uint32_t c; asm volatile("mov.b32 %0, %1;" : "=r"(c) : "f"(S1[i])); S1[i] = __uint_as_float(c); }
      PROF(38);
    }
    const int tid = threadIdx.x;
    if (tid == 0) {
      unsigned old = atomicAdd(&g_flags.done.v, 1);
      if (old == ep1 * NMAIN - 1) {
        asm volatile("st.relaxed.gpu.global.u32 [%0], %1;" :: "l"(&g_flags.epoch.v), "r"(ep1) : "memory");
      }
    }
    __syncwarp();
    cluster_sync();
  }
}

typedef CUresult (*PFN_encode)(CUtensorMap*, CUtensorMapDataType, cuuint32_t, void*, const cuuint64_t*, const cuuint64_t*,
                               const cuuint32_t*, const cuuint32_t*, CUtensorMapInterleave, CUtensorMapSwizzle,
                               CUtensorMapL2promotion, CUtensorMapFloatOOBfill);

CUtensorMap make_map(PFN_encode enc, const void* ptr, uint64_t inner, uint64_t outer, uint32_t box_inner, uint32_t box_outer,
                     CUtensorMapSwizzle swz = CU_TENSOR_MAP_SWIZZLE_128B) {
  CUtensorMap m;
  cuuint64_t dims[2] = {inner, outer};
  cuuint64_t strides[1] = {inner * 2};
  cuuint32_t box[2] = {box_inner, box_outer};
  cuuint32_t es[2] = {1, 1};
  enc(&m, CU_TENSOR_MAP_DATA_TYPE_BFLOAT16, 2, const_cast<void*>(ptr), dims, strides, box, es, CU_TENSOR_MAP_INTERLEAVE_NONE,
      swz, CU_TENSOR_MAP_L2_PROMOTION_L2_256B, CU_TENSOR_MAP_FLOAT_OOB_FILL_NONE);
  return m;
}

}

extern "C" void kernel_launch(void* const* d_in, const int* in_sizes, int n_in, void* d_out, int out_size) {
  (void)in_sizes; (void)n_in; (void)out_size;
  static PFN_encode enc = nullptr;
  if (!enc) {
    void* fn = nullptr;
    cudaDriverEntryPointQueryResult qr;
    cudaGetDriverEntryPoint("cuTensorMapEncodeTiled", &fn, cudaEnableDefault, &qr);
    enc = (PFN_encode)fn;
    cudaFuncSetAttribute(mega_kernel, cudaFuncAttributeMaxDynamicSharedMemorySize, SMEM_BYTES);
  }
  Params prm;
  prm.x0 = (const __nv_bfloat16*)d_in[0];
  prm.wA_qkv = (const __nv_bfloat16*)d_in[1];
  prm.wA_o = (const __nv_bfloat16*)d_in[2];
  prm.wB_qkv = (const __nv_bfloat16*)d_in[4];
  prm.wB_phi = (const __nv_bfloat16*)d_in[5];
  prm.wB_o = (const __nv_bfloat16*)d_in[6];
  prm.out = (__nv_bfloat16*)d_out;
  void *obuf = nullptr, *wf = nullptr;
  cudaGetSymbolAddress(&obuf, g_obuf);
  cudaGetSymbolAddress(&wf, g_wfold);
  CUtensorMap tm_x0 = make_map(enc, d_in[0], D_MODEL, S_LEN, 64, 128);
  CUtensorMap tm_xo = make_map(enc, d_out, D_MODEL, S_LEN, 64, 16);
  CUtensorMap tm_os = make_map(enc, obuf, D_MODEL, 2 * S_LEN, 64, 16);
  CUtensorMap tm_o = make_map(enc, obuf, D_MODEL, 2 * S_LEN, 64, 128);
  CUtensorMap tm_wf = make_map(enc, wf, 2048, D_MODEL, 64, 32);
  CUtensorMap tm_wqA = make_map(enc, d_in[1], 3 * D_MODEL, D_MODEL, 64, 32);
  CUtensorMap tm_wqB = make_map(enc, prm.wB_qkv, 3 * D_MODEL, D_MODEL, 64, 32);
  CUtensorMap tm_woA = make_map(enc, prm.wA_o, D_MODEL, D_MODEL, 64, 64);
  CUtensorMap tm_woB = make_map(enc, prm.wB_o, D_MODEL, D_MODEL, 64, 64);
  CUtensorMap tm_phi = make_map(enc, prm.wB_phi, 32, 1024, 32, 128, CU_TENSOR_MAP_SWIZZLE_64B);
  mega_kernel<<<NMAIN + NAUX, 384, SMEM_BYTES>>>(tm_x0, tm_xo, tm_os, tm_o, tm_wf, tm_wqA, tm_wqB, tm_woA, tm_woB, tm_phi, prm);
}
```

```cpp
#include <cuda_runtime.h>
#include <cuda.h>
#include <cuda_bf16.h>
#include <stdint.h>

#define NLAYERS 4

#define STAG1 0
#define HPUMP1 2
#define HPUMP2 1
#define ASKEW 2
#define FPUMP 3
#define PFGAP 100
#define POLLGAP 120
#define OW 1
#define AW0 1
#define RLATE 3
#define FSTART 0
#define MAPV 1
#define HW1 29
#define XPACE 0x06050401000000ull
#define XP0 4
#define HW0 18
#define XD 4
#define WFGAP 50
#define KT0 2
#define W23 0
#define AX 0
#define PF0 1
#define EARLY 2
#define KVL 1
#define BMASK 0x1F
#define ASITE 1
namespace {

constexpr int S_LEN = 2048, D_MODEL = 1024;
constexpr int NAUX = 4, NMAIN = 128;
constexpr int SLOT = 16384;
constexpr int QST = 24576;
constexpr int OFF_RA = 6 * SLOT, OFF_S = 10 * SLOT;
constexpr int OFF_HALO = 13 * SLOT, OFF_LNB = OFF_HALO  , OFF_ONES = OFF_HALO + 3072;
constexpr int OFF_ST = OFF_HALO + 7168  , OFF_PHI = OFF_HALO + 8192;
constexpr int OFF_BAR = 14 * SLOT;
constexpr int OFF_LNA = OFF_BAR + 1024;
constexpr int SMEM_BYTES = OFF_LNA + 2048;
#define WO_ASLOT(par) ((par) ? 0x9876CAB39876CA98ull : 0x98C76BA398C7698Cull)
constexpr unsigned long long WO_BSLOT = 0x5432105421054210ull;
__device__ __forceinline__ int srcb(int j, int i) { return (i + (i >= j)) & 7; }
__device__ __forceinline__ int kslice(int j, int i) { return i < 2 ? 2 * j + i : (i < 9 ? 2 * srcb(j, i - 2) : 2 * srcb(j, i - 9) + 1); }
__device__ __forceinline__ int wslice(int j, int s) { return 2 * ((s & 7) ? srcb(j, (s & 7) - 1) : j) + (s >> 3); }
constexpr int KVH = 6 * 128 * 4;

struct __align__(128) Flag { unsigned v; unsigned pad[31]; };
struct Flags {
  Flag xready[4][16];
  Flag wfready[8];
  Flag done;
  Flag epoch;
};

__device__ Flags g_flags;
__device__ __nv_bfloat16 g_obuf[2 * S_LEN * D_MODEL];
#define O_BIT(l) ((epoch * NLAYERS + (l) + 1) & 1u)
#define X_BIT(l) ((epoch * (NLAYERS - 1) + (l) + 1) & 1u)
__device__ __nv_bfloat16 g_wfold[D_MODEL * 2048];
__device__ uint4 g_halo[16 * 8 * 512];
__device__ __align__(128) float g_kv[2][32 * KVH];
__device__ __align__(128) uint2 g_colsum[2][1536][2];
__device__ __align__(128) uint2 g_stats[S_LEN * 8];
#define H_BIT(l) (NLAYERS > 2 ? (uint32_t)((l) == 0) : (ep1 & 1))
#define STAT_TAG(l) ((ep1 * NLAYERS + (l) + 1) & 3u)

#define RETRY_COUNT()
#define PRL 0
#define PRU 0
#define PROFL 1
#define PROFW 0
#define PROFT(i) do {} while (0)
#define PROF(i) do {} while (0)

__device__ __forceinline__ uint32_t smem_u32(const void* p) { return (uint32_t)__cvta_generic_to_shared(p); }
__device__ __forceinline__ bool elect_one() {
  uint32_t p;
  asm volatile("{\n.reg .pred p;\nelect.sync _|p, 0xffffffff;\nselp.u32 %0, 1, 0, p;\n}\n" : "=r"(p));
  return p != 0;
}
__device__ __forceinline__ void mbar_init(uint32_t bar, uint32_t cnt) {
  asm volatile("mbarrier.init.shared::cta.b64 [%0], %1;" :: "r"(bar), "r"(cnt));
}
__device__ __forceinline__ void mbar_expect_tx(uint32_t bar, uint32_t bytes) {
  asm volatile("mbarrier.arrive.expect_tx.shared::cta.b64 _, [%0], %1;" :: "r"(bar), "r"(bytes) : "memory");
}
#define mbar_wait(bar, parity) \
  asm volatile("{\n.reg .pred p, q;\nW_%=:\nmbarrier.try_wait.parity.shared::cta.b64 p, [%1], %2;\nadd.s32 %0, %0, -1;\n" \
               "setp.gt.and.s32 q, %0, 0, !p;\n@q bra.uni W_%=;\n}\n" : "+r"(budget) : "r"((uint32_t)(bar)), "r"((uint32_t)(parity)) : "memory")
#define mbar_wait_sl(bar, parity) \
  asm volatile("{\n.reg .pred p, q;\nW_%=:\nmbarrier.try_wait.parity.shared::cta.b64 p, [%1], %2, 20000;\nadd.s32 %0, %0, -64;\n" \
               "setp.gt.and.s32 q, %0, 0, !p;\n@q bra.uni W_%=;\n}\n" : "+r"(budget) : "r"((uint32_t)(bar)), "r"((uint32_t)(parity)) : "memory")
__device__ __forceinline__ void mbar_arrive_local(uint32_t bar) {
  asm volatile("mbarrier.arrive.shared::cta.b64 _, [%0];" :: "r"(bar) : "memory");
}
__device__ __forceinline__ void tma_load_2d(uint32_t dst, const CUtensorMap* tm, uint32_t bar, int c0, int c1) {
  asm volatile("cp.async.bulk.tensor.2d.shared::cluster.global.mbarrier::complete_tx::bytes [%0], [%1, {%3, %4}], [%2];"
               :: "r"(dst), "l"(tm), "r"(bar), "r"(c0), "r"(c1) : "memory");
}
__device__ __forceinline__ void tma_load_2d_mc(uint32_t dst, const CUtensorMap* tm, uint32_t bar, int c0, int c1) {
  asm volatile("cp.async.bulk.tensor.2d.shared::cluster.global.mbarrier::complete_tx::bytes.multicast::cluster [%0], [%1, {%3, %4}], [%2], %5;"
               :: "r"(dst), "l"(tm), "r"(bar), "r"(c0), "r"(c1), "h"((uint16_t)3) : "memory");
}
__device__ __forceinline__ void tma_store_2d(const CUtensorMap* tm, uint32_t src, int c0, int c1) {
  asm volatile("cp.async.bulk.tensor.2d.global.shared::cta.bulk_group [%0, {%2, %3}], [%1];"
               :: "l"(tm), "r"(src), "r"(c0), "r"(c1) : "memory");
}
__device__ __forceinline__ void bulk_commit_wait() {
  asm volatile("cp.async.bulk.commit_group;\ncp.async.bulk.wait_group 0;" ::: "memory");
}
__device__ __forceinline__ void prefetch_tmap(const CUtensorMap* tm) {
  asm volatile("prefetch.tensormap [%0];" :: "l"(tm) : "memory");
}
__device__ __forceinline__ void fence_proxy_async_global() { asm volatile("fence.proxy.async.global;" ::: "memory"); }
__device__ __forceinline__ void fence_proxy_async_smem() { asm volatile("fence.proxy.async.shared::cta;" ::: "memory"); }
__device__ __forceinline__ unsigned ld_relaxed(const unsigned* p) {
  unsigned v;
  asm volatile("ld.relaxed.gpu.global.u32 %0, [%1];" : "=r"(v) : "l"(p) : "memory");
  return v;
}
__device__ __forceinline__ void fence_acquire() { asm volatile("fence.acquire.gpu;" ::: "memory"); }
__device__ __forceinline__ void wait_flag(const unsigned* p, unsigned target) {
  int it = 0;
  while ((int)(ld_relaxed(p) - target) < 0 && ++it < (1 << 20)) {}
  fence_acquire();
}
__device__ __forceinline__ void signal_release(unsigned* p) {
  asm volatile("red.release.gpu.global.add.u32 [%0], 1;" :: "l"(p) : "memory");
}
template <int ID, int N> __device__ __forceinline__ void bar_arrive() { asm volatile("bar.arrive %0, %1;" :: "n"(ID), "n"(N) : "memory"); }
template <int ID, int N> __device__ __forceinline__ void bar_sync() { asm volatile("bar.sync %0, %1;" :: "n"(ID), "n"(N) : "memory"); }
__device__ __forceinline__ void bar_wg(int wg) { asm volatile("bar.sync %0, 128;" :: "r"(2 + wg) : "memory"); }
__device__ __forceinline__ void cluster_sync() {
  asm volatile("barrier.cluster.arrive.relaxed.aligned;\nbarrier.cluster.wait.aligned;" ::: "memory");
}
__device__ __forceinline__ void cluster_wait() { asm volatile("barrier.cluster.wait.acquire.aligned;" ::: "memory"); }
enum { BAR_X1 = 7, BAR_WF = 8  , BAR_SKEW = 10 };

__device__ __forceinline__ void wgmma_fence() { asm volatile("wgmma.fence.sync.aligned;" ::: "memory"); }
__device__ __forceinline__ void wgmma_commit() { asm volatile("wgmma.commit_group.sync.aligned;" ::: "memory"); }
template <int N> __device__ __forceinline__ void wgmma_wait() { asm volatile("wgmma.wait_group.sync.aligned %0;" :: "n"(N) : "memory"); }

template <int scale_d, int tnsp_b = 1> __device__ __forceinline__ void wgmma_n192(float* d, uint64_t descA, uint64_t descB) {
  asm volatile("{\n.reg .pred p;\nsetp.ne.b32 p, %98, 0;\n"
               "wgmma.mma_async.sync.aligned.m64n192k16.f32.bf16.bf16 {%0,%1,%2,%3,%4,%5,%6,%7,%8,%9,%10,%11,%12,%13,%14,%15,%16,%17,%18,%19,%20,%21,%22,%23,%24,%25,%26,%27,%28,%29,%30,%31,%32,%33,%34,%35,%36,%37,%38,%39,%40,%41,%42,%43,%44,%45,%46,%47,%48,%49,%50,%51,%52,%53,%54,%55,%56,%57,%58,%59,%60,%61,%62,%63,%64,%65,%66,%67,%68,%69,%70,%71,%72,%73,%74,%75,%76,%77,%78,%79,%80,%81,%82,%83,%84,%85,%86,%87,%88,%89,%90,%91,%92,%93,%94,%95}, %96, %97, p, 1, 1, 0, %99;\n}\n"
               : "+f"(d[0]), "+f"(d[1]), "+f"(d[2]), "+f"(d[3]), "+f"(d[4]), "+f"(d[5]), "+f"(d[6]), "+f"(d[7]), "+f"(d[8]), "+f"(d[9]), "+f"(d[10]), "+f"(d[11]), "+f"(d[12]), "+f"(d[13]), "+f"(d[14]), "+f"(d[15]), "+f"(d[16]), "+f"(d[17]), "+f"(d[18]), "+f"(d[19]), "+f"(d[20]), "+f"(d[21]), "+f"(d[22]), "+f"(d[23]), "+f"(d[24]), "+f"(d[25]), "+f"(d[26]), "+f"(d[27]), "+f"(d[28]), "+f"(d[29]), "+f"(d[30]), "+f"(d[31]), "+f"(d[32]), "+f"(d[33]), "+f"(d[34]), "+f"(d[35]), "+f"(d[36]), "+f"(d[37]), "+f"(d[38]), "+f"(d[39]), "+f"(d[40]), "+f"(d[41]), "+f"(d[42]), "+f"(d[43]), "+f"(d[44]), "+f"(d[45]), "+f"(d[46]), "+f"(d[47]), "+f"(d[48]), "+f"(d[49]), "+f"(d[50]), "+f"(d[51]), "+f"(d[52]), "+f"(d[53]), "+f"(d[54]), "+f"(d[55]), "+f"(d[56]), "+f"(d[57]), "+f"(d[58]), "+f"(d[59]), "+f"(d[60]), "+f"(d[61]), "+f"(d[62]), "+f"(d[63]), "+f"(d[64]), "+f"(d[65]), "+f"(d[66]), "+f"(d[67]), "+f"(d[68]), "+f"(d[69]), "+f"(d[70]), "+f"(d[71]), "+f"(d[72]), "+f"(d[73]), "+f"(d[74]), "+f"(d[75]), "+f"(d[76]), "+f"(d[77]), "+f"(d[78]), "+f"(d[79]), "+f"(d[80]), "+f"(d[81]), "+f"(d[82]), "+f"(d[83]), "+f"(d[84]), "+f"(d[85]), "+f"(d[86]), "+f"(d[87]), "+f"(d[88]), "+f"(d[89]), "+f"(d[90]), "+f"(d[91]), "+f"(d[92]), "+f"(d[93]), "+f"(d[94]), "+f"(d[95])
               : "l"(descA), "l"(descB), "n"(scale_d), "n"(tnsp_b));
}
template <int scale_d> __device__ __forceinline__ void wgmma4_n192(float* d, uint32_t da, uint32_t db) {
#define R_ "{%0,%1,%2,%3,%4,%5,%6,%7,%8,%9,%10,%11,%12,%13,%14,%15,%16,%17,%18,%19,%20,%21,%22,%23,%24,%25,%26,%27,%28,%29,%30,%31,%32,%33,%34,%35,%36,%37,%38,%39,%40,%41,%42,%43,%44,%45,%46,%47,%48,%49,%50,%51,%52,%53,%54,%55,%56,%57,%58,%59,%60,%61,%62,%63,%64,%65,%66,%67,%68,%69,%70,%71,%72,%73,%74,%75,%76,%77,%78,%79,%80,%81,%82,%83,%84,%85,%86,%87,%88,%89,%90,%91,%92,%93,%94,%95}"
  asm volatile("{\n.reg .pred p, q;\n.reg .b64 a, b;\nsetp.ne.b32 p, %98, 0;\nsetp.eq.b32 q, 0, 0;\nmov.b64 a, {%96, 0x40000040};\nmov.b64 b, {%97, 0x40000040};\n"
               "wgmma.mma_async.sync.aligned.m64n192k16.f32.bf16.bf16 " R_ ", a, b, p, 1, 1, 0, 1;\nadd.s64 a, a, 2;\nadd.s64 b, b, 128;\n"
               "wgmma.mma_async.sync.aligned.m64n192k16.f32.bf16.bf16 " R_ ", a, b, q, 1, 1, 0, 1;\nadd.s64 a, a, 2;\nadd.s64 b, b, 128;\n"
               "wgmma.mma_async.sync.aligned.m64n192k16.f32.bf16.bf16 " R_ ", a, b, q, 1, 1, 0, 1;\nadd.s64 a, a, 2;\nadd.s64 b, b, 128;\n"
               "wgmma.mma_async.sync.aligned.m64n192k16.f32.bf16.bf16 " R_ ", a, b, q, 1, 1, 0, 1;\n}\n"
               : "+f"(d[0]), "+f"(d[1]), "+f"(d[2]), "+f"(d[3]), "+f"(d[4]), "+f"(d[5]), "+f"(d[6]), "+f"(d[7]), "+f"(d[8]), "+f"(d[9]), "+f"(d[10]), "+f"(d[11]), "+f"(d[12]), "+f"(d[13]), "+f"(d[14]), "+f"(d[15]), "+f"(d[16]), "+f"(d[17]), "+f"(d[18]), "+f"(d[19]), "+f"(d[20]), "+f"(d[21]), "+f"(d[22]), "+f"(d[23]), "+f"(d[24]), "+f"(d[25]), "+f"(d[26]), "+f"(d[27]), "+f"(d[28]), "+f"(d[29]), "+f"(d[30]), "+f"(d[31]), "+f"(d[32]), "+f"(d[33]), "+f"(d[34]), "+f"(d[35]), "+f"(d[36]), "+f"(d[37]), "+f"(d[38]), "+f"(d[39]), "+f"(d[40]), "+f"(d[41]), "+f"(d[42]), "+f"(d[43]), "+f"(d[44]), "+f"(d[45]), "+f"(d[46]), "+f"(d[47]), "+f"(d[48]), "+f"(d[49]), "+f"(d[50]), "+f"(d[51]), "+f"(d[52]), "+f"(d[53]), "+f"(d[54]), "+f"(d[55]), "+f"(d[56]), "+f"(d[57]), "+f"(d[58]), "+f"(d[59]), "+f"(d[60]), "+f"(d[61]), "+f"(d[62]), "+f"(d[63]), "+f"(d[64]), "+f"(d[65]), "+f"(d[66]), "+f"(d[67]), "+f"(d[68]), "+f"(d[69]), "+f"(d[70]), "+f"(d[71]), "+f"(d[72]), "+f"(d[73]), "+f"(d[74]), "+f"(d[75]), "+f"(d[76]), "+f"(d[77]), "+f"(d[78]), "+f"(d[79]), "+f"(d[80]), "+f"(d[81]), "+f"(d[82]), "+f"(d[83]), "+f"(d[84]), "+f"(d[85]), "+f"(d[86]), "+f"(d[87]), "+f"(d[88]), "+f"(d[89]), "+f"(d[90]), "+f"(d[91]), "+f"(d[92]), "+f"(d[93]), "+f"(d[94]), "+f"(d[95])
               : "r"(da), "r"(db), "n"(scale_d));
#undef R_
}
template <int scale_d> __device__ __forceinline__ void wgmma4_n128(float* d, uint32_t da, uint32_t db) {
#define R_ "{%0,%1,%2,%3,%4,%5,%6,%7,%8,%9,%10,%11,%12,%13,%14,%15,%16,%17,%18,%19,%20,%21,%22,%23,%24,%25,%26,%27,%28,%29,%30,%31,%32,%33,%34,%35,%36,%37,%38,%39,%40,%41,%42,%43,%44,%45,%46,%47,%48,%49,%50,%51,%52,%53,%54,%55,%56,%57,%58,%59,%60,%61,%62,%63}"
  asm volatile("{\n.reg .pred p, q;\n.reg .b64 a, b;\nsetp.ne.b32 p, %66, 0;\nsetp.eq.b32 q, 0, 0;\nmov.b64 a, {%64, 0x40000040};\nmov.b64 b, {%65, 0x40000040};\n"
               "wgmma.mma_async.sync.aligned.m64n128k16.f32.bf16.bf16 " R_ ", a, b, p, 1, 1, 0, 1;\nadd.s64 a, a, 2;\nadd.s64 b, b, 128;\n"
               "wgmma.mma_async.sync.aligned.m64n128k16.f32.bf16.bf16 " R_ ", a, b, q, 1, 1, 0, 1;\nadd.s64 a, a, 2;\nadd.s64 b, b, 128;\n"
               "wgmma.mma_async.sync.aligned.m64n128k16.f32.bf16.bf16 " R_ ", a, b, q, 1, 1, 0, 1;\nadd.s64 a, a, 2;\nadd.s64 b, b, 128;\n"
               "wgmma.mma_async.sync.aligned.m64n128k16.f32.bf16.bf16 " R_ ", a, b, q, 1, 1, 0, 1;\n}\n"
               : "+f"(d[0]), "+f"(d[1]), "+f"(d[2]), "+f"(d[3]), "+f"(d[4]), "+f"(d[5]), "+f"(d[6]), "+f"(d[7]), "+f"(d[8]), "+f"(d[9]), "+f"(d[10]), "+f"(d[11]), "+f"(d[12]), "+f"(d[13]), "+f"(d[14]), "+f"(d[15]), "+f"(d[16]), "+f"(d[17]), "+f"(d[18]), "+f"(d[19]), "+f"(d[20]), "+f"(d[21]), "+f"(d[22]), "+f"(d[23]), "+f"(d[24]), "+f"(d[25]), "+f"(d[26]), "+f"(d[27]), "+f"(d[28]), "+f"(d[29]), "+f"(d[30]), "+f"(d[31]), "+f"(d[32]), "+f"(d[33]), "+f"(d[34]), "+f"(d[35]), "+f"(d[36]), "+f"(d[37]), "+f"(d[38]), "+f"(d[39]), "+f"(d[40]), "+f"(d[41]), "+f"(d[42]), "+f"(d[43]), "+f"(d[44]), "+f"(d[45]), "+f"(d[46]), "+f"(d[47]), "+f"(d[48]), "+f"(d[49]), "+f"(d[50]), "+f"(d[51]), "+f"(d[52]), "+f"(d[53]), "+f"(d[54]), "+f"(d[55]), "+f"(d[56]), "+f"(d[57]), "+f"(d[58]), "+f"(d[59]), "+f"(d[60]), "+f"(d[61]), "+f"(d[62]), "+f"(d[63])
               : "r"(da), "r"(db), "n"(scale_d));
#undef R_
}
template <int scale_d> __device__ __forceinline__ void wgmma_n32(float* d, uint64_t descA, uint64_t descB) {
  asm volatile("{\n.reg .pred p;\nsetp.ne.b32 p, %18, 0;\n"
               "wgmma.mma_async.sync.aligned.m64n32k16.f32.bf16.bf16 {%0,%1,%2,%3,%4,%5,%6,%7,%8,%9,%10,%11,%12,%13,%14,%15}, %16, %17, p, 1, 1, 0, 1;\n}\n"
               : "+f"(d[0]), "+f"(d[1]), "+f"(d[2]), "+f"(d[3]), "+f"(d[4]), "+f"(d[5]), "+f"(d[6]), "+f"(d[7]), "+f"(d[8]), "+f"(d[9]), "+f"(d[10]), "+f"(d[11]), "+f"(d[12]), "+f"(d[13]), "+f"(d[14]), "+f"(d[15])
               : "l"(descA), "l"(descB), "n"(scale_d));
}
template <int scale_d, int tnsp_a> __device__ __forceinline__ void wgmma_n40(float* d, uint64_t descA, uint64_t descB) {
  asm volatile("{\n.reg .pred p;\nsetp.ne.b32 p, %22, 0;\n"
               "wgmma.mma_async.sync.aligned.m64n40k16.f32.bf16.bf16 {%0,%1,%2,%3,%4,%5,%6,%7,%8,%9,%10,%11,%12,%13,%14,%15,%16,%17,%18,%19}, %20, %21, p, 1, 1, %23, 1;\n}\n"
               : "+f"(d[0]), "+f"(d[1]), "+f"(d[2]), "+f"(d[3]), "+f"(d[4]), "+f"(d[5]), "+f"(d[6]), "+f"(d[7]), "+f"(d[8]), "+f"(d[9]), "+f"(d[10]), "+f"(d[11]), "+f"(d[12]), "+f"(d[13]), "+f"(d[14]), "+f"(d[15]), "+f"(d[16]), "+f"(d[17]), "+f"(d[18]), "+f"(d[19])
               : "l"(descA), "l"(descB), "n"(scale_d), "n"(tnsp_a));
}
template <int scale_d> __device__ __forceinline__ void wgmma_n40_rs(float* d, const uint32_t* a, uint64_t descB) {
  asm volatile("{\n.reg .pred p;\nsetp.ne.b32 p, %25, 0;\n"
               "wgmma.mma_async.sync.aligned.m64n40k16.f32.bf16.bf16 {%0,%1,%2,%3,%4,%5,%6,%7,%8,%9,%10,%11,%12,%13,%14,%15,%16,%17,%18,%19}, {%20,%21,%22,%23}, %24, p, 1, 1, 1;\n}\n"
               : "+f"(d[0]), "+f"(d[1]), "+f"(d[2]), "+f"(d[3]), "+f"(d[4]), "+f"(d[5]), "+f"(d[6]), "+f"(d[7]), "+f"(d[8]), "+f"(d[9]), "+f"(d[10]), "+f"(d[11]), "+f"(d[12]), "+f"(d[13]), "+f"(d[14]), "+f"(d[15]), "+f"(d[16]), "+f"(d[17]), "+f"(d[18]), "+f"(d[19])
               : "r"(a[0]), "r"(a[1]), "r"(a[2]), "r"(a[3]), "l"(descB), "n"(scale_d));
}
__device__ __forceinline__ uint64_t make_desc(uint32_t addr, uint32_t lbo_bytes, uint32_t sbo_bytes) {
  return (uint64_t)((addr & 0x3FFFF) >> 4) | ((uint64_t)(lbo_bytes >> 4) << 16) | ((uint64_t)(sbo_bytes >> 4) << 32) | (1ull << 62);
}

__device__ __forceinline__ void ldsm_x4(uint32_t addr, uint32_t& r0, uint32_t& r1, uint32_t& r2, uint32_t& r3) {
  asm volatile("ldmatrix.sync.aligned.m8n8.x4.shared.b16 {%0,%1,%2,%3}, [%4];" : "=r"(r0), "=r"(r1), "=r"(r2), "=r"(r3) : "r"(addr) : "memory");
}
__device__ __forceinline__ void ldsm_x4_t(uint32_t addr, uint32_t& r0, uint32_t& r1, uint32_t& r2, uint32_t& r3) {
  asm volatile("ldmatrix.sync.aligned.m8n8.x4.trans.shared.b16 {%0,%1,%2,%3}, [%4];" : "=r"(r0), "=r"(r1), "=r"(r2), "=r"(r3) : "r"(addr) : "memory");
}
__device__ __forceinline__ void stsm_x4(uint32_t addr, uint32_t r0, uint32_t r1, uint32_t r2, uint32_t r3) {
  asm volatile("stmatrix.sync.aligned.m8n8.x4.shared.b16 [%0], {%1,%2,%3,%4};" :: "r"(addr), "r"(r0), "r"(r1), "r"(r2), "r"(r3) : "memory");
}
__device__ __forceinline__ void sts128(uint32_t addr, uint32_t a, uint32_t b, uint32_t c, uint32_t d) {
  asm volatile("st.shared.v4.u32 [%0], {%1,%2,%3,%4};" :: "r"(addr), "r"(a), "r"(b), "r"(c), "r"(d) : "memory");
}
__device__ __forceinline__ float lds32f(uint32_t addr) {
  float v;
  asm volatile("ld.shared.f32 %0, [%1];" : "=f"(v) : "r"(addr) : "memory");
  return v;
}
__device__ __forceinline__ void sts32f(uint32_t addr, float a) {
  asm volatile("st.shared.f32 [%0], %1;" :: "r"(addr), "f"(a) : "memory");
}
__device__ __forceinline__ void mma_bf16(float (&c)[4], uint32_t a0, uint32_t a1, uint32_t a2, uint32_t a3, uint32_t b0, uint32_t b1) {
  asm volatile("mma.sync.aligned.m16n8k16.row.col.f32.bf16.bf16.f32 {%0,%1,%2,%3}, {%4,%5,%6,%7}, {%8,%9}, {%0,%1,%2,%3};"
               : "+f"(c[0]), "+f"(c[1]), "+f"(c[2]), "+f"(c[3]) : "r"(a0), "r"(a1), "r"(a2), "r"(a3), "r"(b0), "r"(b1));
}
__device__ __forceinline__ void mma_bf16_z(float (&c)[4], uint32_t a0, uint32_t a1, uint32_t a2, uint32_t a3, uint32_t b0, uint32_t b1) {
  asm volatile("mma.sync.aligned.m16n8k16.row.col.f32.bf16.bf16.f32 {%0,%1,%2,%3}, {%4,%5,%6,%7}, {%8,%9}, {%10,%10,%10,%10};"
               : "=f"(c[0]), "=f"(c[1]), "=f"(c[2]), "=f"(c[3]) : "r"(a0), "r"(a1), "r"(a2), "r"(a3), "r"(b0), "r"(b1), "f"(0.f));
}
__device__ __forceinline__ uint32_t movm_t(uint32_t v) {
  uint32_t r;
  asm volatile("movmatrix.sync.aligned.m8n8.trans.b16 %0, %1;" : "=r"(r) : "r"(v));
  return r;
}
__device__ __forceinline__ uint32_t pack_bf16(float lo, float hi) {
  uint32_t r;
  asm("cvt.rn.bf16x2.f32 %0, %1, %2;" : "=r"(r) : "f"(hi), "f"(lo));
  return r;
}
__device__ __forceinline__ float bf_lo(uint32_t v) { return __uint_as_float(v << 16); }
__device__ __forceinline__ float bf_hi(uint32_t v) { return __uint_as_float(v & 0xFFFF0000u); }
__device__ __forceinline__ void split3(float x, uint32_t& h, uint32_t& m, uint32_t& l) {
  h = pack_bf16(x, 0.f); x -= bf_lo(h);
  m = pack_bf16(x, 0.f); x -= bf_lo(m);
  l = pack_bf16(x, 0.f);
}
__device__ __forceinline__ float ex2(float x) { float r; asm("ex2.approx.ftz.f32 %0, %1;" : "=f"(r) : "f"(x)); return r; }
__device__ __forceinline__ float rcp_fast(float x) { float r; asm("rcp.approx.ftz.f32 %0, %1;" : "=f"(r) : "f"(x)); return r; }
__device__ __forceinline__ void red_v4(float* p, float a, float b, float c, float d) {
  asm volatile("red.global.add.v4.f32 [%0], {%1, %2, %3, %4};" :: "l"(p), "f"(a), "f"(b), "f"(c), "f"(d) : "memory");
}
__device__ __forceinline__ uint4 ld_ll(const uint4* p) {
  uint4 v;
  asm volatile("{\n.reg .b64 a, b;\nld.relaxed.gpu.global.v2.b64 {a, b}, [%4];\nmov.b64 {%0, %1}, a;\nmov.b64 {%2, %3}, b;\n}\n"
               : "=r"(v.x), "=r"(v.y), "=r"(v.z), "=r"(v.w) : "l"(p) : "memory");
  return v;
}
__device__ __forceinline__ void st_b64(uint2* p, uint32_t a, uint32_t b) {
  asm volatile("{\n.reg .b64 v;\nmov.b64 v, {%1, %2};\nst.relaxed.gpu.global.b64 [%0], v;\n}\n" :: "l"(p), "r"(a), "r"(b) : "memory");
}
__device__ __forceinline__ void st_b128(uint4* p, uint32_t a, uint32_t b, uint32_t c, uint32_t d) {
  asm volatile("{\n.reg .b128 v;\nmov.b128 v, {%1, %2, %3, %4};\nst.relaxed.gpu.global.b128 [%0], v;\n}\n" :: "l"(p), "r"(a), "r"(b), "r"(c), "r"(d) : "memory");
}
__device__ __forceinline__ uint4 ld_b128(const uint4* p) {
  uint4 v;
  asm volatile("{\n.reg .b128 v;\nld.relaxed.gpu.global.b128 v, [%4];\nmov.b128 {%0, %1, %2, %3}, v;\n}\n" : "=r"(v.x), "=r"(v.y), "=r"(v.z), "=r"(v.w) : "l"(p) : "memory");
  return v;
}

constexpr float LOG2E = 1.4426950408889634f;

struct Params {
  const __nv_bfloat16* x0;
  const __nv_bfloat16* wA_qkv;
  const __nv_bfloat16* wA_o;
  const __nv_bfloat16* wB_qkv;
  const __nv_bfloat16* wB_phi;
  const __nv_bfloat16* wB_o;
  __nv_bfloat16* out;
};

#define ACC_DEF(d, n) _Pragma("unroll") for (int i_ = 0; i_ < (n); i_++) asm volatile("" : "=f"(d[i_]))
#define ACC_FENCE(d, n) _Pragma("unroll") for (int i_ = 0; i_ < (n); i_++) asm volatile("" : "+f"(d[i_]) :: "memory")
#define PIN(a, n) _Pragma("unroll") for (int i_ = 0; i_ < (n); i_++) asm volatile("" : "+f"((a)[i_]))
#define PINU(a, n) _Pragma("unroll") for (int i_ = 0; i_ < (n); i_++) asm volatile("" : "+r"((a)[i_]))

#define STAGE_V(acc, p0) { \
    _Pragma("unroll") for (int j_ = 0; j_ < 4; j_++) { \
      const float* a_ = (acc) + j_ * 8; \
      stsm_x4((p0) + (j_ >> 1) * 8192 + (srowoff >> 1) + ((((uint32_t)(j_ & 1) << 5) + lhi) ^ lsw2), \
              pack_bf16(rs0 * a_[0], rs0 * a_[1]), pack_bf16(rs1 * a_[2], rs1 * a_[3]), pack_bf16(rs0 * a_[4], rs0 * a_[5]), pack_bf16(rs1 * a_[6], rs1 * a_[7])); } }
#define FRAG(dst, acc, TR, grp) { \
    _Pragma("unroll") for (int i_ = 0; i_ < 16; i_++) { \
      const float r_ = (i_ & 1) ? rs1 : rs0; \
      const uint32_t w_ = pack_bf16(r_ * (acc)[2 * i_], r_ * (acc)[2 * i_ + 1]); \
      if (TR) (dst)[i_] = movm_t(w_); else (dst)[(i_ & 12) + (i_ & 1) * 2 + ((i_ >> 1) & 1)] = w_; } \
    if (warp == 7 && mm < 15) { \
      _Pragma("unroll") for (int j_ = 0; j_ < 4; j_++) \
        st_b128(g_halo + (size_t)(mm * 8 + jj) * 512 + ((grp) * 4 + j_) * 32 + lane, ((dst)[j_ * 4] & ~1u) | H_BIT(l), (dst)[j_ * 4 + 1], (dst)[j_ * 4 + 2], (dst)[j_ * 4 + 3]); } \
    PINU(dst, 16); }
#define FRAG_PUT(src, slot) if (warp < 7) { _Pragma("unroll") for (int j_ = 0; j_ < 4; j_++) \
      sts128(sbase + (slot) * SLOT + 2048 + warp * 2048 + j_ * 512 + lane * 16, (src)[j_ * 4], (src)[j_ * 4 + 1], (src)[j_ * 4 + 2], (src)[j_ * 4 + 3]); }
#define FRAG_GET(dst, slot) { _Pragma("unroll") for (int j_ = 0; j_ < 4; j_++) \
      asm volatile("ld.shared.v4.u32 {%0, %1, %2, %3}, [%4];" : "=r"((dst)[j_ * 4]), "=r"((dst)[j_ * 4 + 1]), "=r"((dst)[j_ * 4 + 2]), "=r"((dst)[j_ * 4 + 3]) \
                   : "r"(sbase + (slot) * SLOT + warp * 2048 + j_ * 512 + lane * 16) : "memory"); }
#define RW(j) (((j) >> 1) * 4 + ((j) & 1))
__device__ __forceinline__ float rmax16(const float* p) {
  float m[4];
#pragma unroll
  for (int j = 0; j < 4; j++) m[j] = fmaxf(fmaxf(p[RW(j)], p[RW(j + 4)]), fmaxf(p[RW(j + 8)], p[RW(j + 12)]));
  const float r = fmaxf(fmaxf(m[0], m[1]), fmaxf(m[2], m[3]));
  return fmaxf(r, __shfl_xor_sync(0xffffffffu, r, 1));
}
__device__ __forceinline__ float rmin16(const float* p) {
  float m[4];
#pragma unroll
  for (int j = 0; j < 4; j++) m[j] = fminf(fminf(p[RW(j)], p[RW(j + 4)]), fminf(p[RW(j + 8)], p[RW(j + 12)]));
  const float r = fminf(fminf(m[0], m[1]), fminf(m[2], m[3]));
  return fminf(r, __shfl_xor_sync(0xffffffffu, r, 1));
}
__device__ __forceinline__ float exps16(float* o, const float* p, float c, float b) {
  float s[4];
#pragma unroll
  for (int j = 0; j < 16; j++) { o[j] = ex2(fmaf(p[RW(j)], c, b)); if (j < 4) s[j] = o[j]; else s[j & 3] += o[j]; }
  return (s[0] + s[1]) + (s[2] + s[3]);
}
__device__ __forceinline__ void store16(const float* e, float sum, uint32_t dst, uint32_t dsw, int c0) {
  const float inv = rcp_fast(sum + __shfl_xor_sync(0xffffffffu, sum, 1));
#pragma unroll
  for (int j = 0; j < 2; j++)
    sts128(dst + (((c0 + j) << 4) ^ dsw), pack_bf16(e[j * 8] * inv, e[j * 8 + 1] * inv), pack_bf16(e[j * 8 + 2] * inv, e[j * 8 + 3] * inv),
           pack_bf16(e[j * 8 + 4] * inv, e[j * 8 + 5] * inv), pack_bf16(e[j * 8 + 6] * inv, e[j * 8 + 7] * inv));
}
__device__ __forceinline__ void expp16(uint32_t* o, const float* p, float c0, float b0, float c1, float b1) {
#pragma unroll
  for (int j = 0; j < 8; j++) {
    const float c = (j & 1) ? c1 : c0, b = (j & 1) ? b1 : b0;
    o[j] = pack_bf16(ex2(fmaf(p[2 * j], c, b)), ex2(fmaf(p[2 * j + 1], c, b)));
  }
}
__device__ __forceinline__ void extrema(float* m, const float* p, float c0, float c1) {
#pragma unroll
  for (int i = 0; i < 4; i++) {
    const float* q = p + (i >> 1) * 16 + (i & 1) * 2;
    m[(i >> 1) * 4 + (i & 1)] = fminf(fminf(fminf(q[0], q[1]), fminf(q[4], q[5])), fminf(fminf(q[8], q[9]), fminf(q[12], q[13])));
    m[(i >> 1) * 4 + (i & 1) + 2] = fmaxf(fmaxf(fmaxf(q[0], q[1]), fmaxf(q[4], q[5])), fmaxf(fmaxf(q[8], q[9]), fmaxf(q[12], q[13])));
  }
#pragma unroll
  for (int o = 1; o <= 2; o <<= 1)
#pragma unroll
    for (int i = 0; i < 8; i++) { const float x = __shfl_xor_sync(0xffffffffu, m[i], o); m[i] = (i & 2) ? fmaxf(m[i], x) : fminf(m[i], x); }
#pragma unroll
  for (int i = 0; i < 8; i++) m[i] *= ((i & 2) ? -1.f : 1.f) * ((i & 1) ? c1 : c0);
}
#define SCHED_FENCE() asm volatile("pmevent 0;" ::: "memory")

__global__ void __cluster_dims__(2, 1, 1) __launch_bounds__(384, 1)
mega_kernel(const __grid_constant__ CUtensorMap tm_x0, const __grid_constant__ CUtensorMap tm_xo, const __grid_constant__ CUtensorMap tm_os,
            const __grid_constant__ CUtensorMap tm_o, const __grid_constant__ CUtensorMap tm_wf,
            const __grid_constant__ CUtensorMap tm_wqA, const __grid_constant__ CUtensorMap tm_wqB,
            const __grid_constant__ CUtensorMap tm_woA, const __grid_constant__ CUtensorMap tm_woB,
            const __grid_constant__ CUtensorMap tm_phi, const Params prm) {
  extern __shared__ __align__(1024) uint8_t smem_raw[];
  const uint32_t sbase = smem_u32(smem_raw);
  const uint32_t bar_full = sbase + OFF_BAR;
  const uint32_t bar_done = bar_full + 384;
  const uint32_t bar_stat = bar_full + 768, bar_stat2 = bar_full + 776, bar_epi = bar_full + 784, bar_phi = bar_full + 936  , bar_halo = bar_full + 904  ;
  const uint32_t bar_xr = bar_full + 800, bar_lx = bar_full + 808, bar_stg = bar_full + 832;
  const uint32_t bar_chk = bar_full + 848;

  const int warp = __shfl_sync(0xffffffffu, threadIdx.x >> 5, 0), lane = threadIdx.x & 31;
  uint32_t rank;
  asm volatile("mov.u32 %0, %%cluster_ctarank;" : "=r"(rank));
  const int aux = (int)blockIdx.x - NMAIN, tp = (int)(blockIdx.x >> 1) - 4;
  const int gp = tp < 0 ? 0 : (tp < 32 ? tp & 7 : 1 + (tp - 32) % 7), me = tp < 0 ? tp + 8 : (tp < 32 ? tp >> 3 : 4 + (tp - 32) / 7);
  const int jj = me, cc = gp;
  const int cta = aux >= 0 ? -1 : (cc * 8 + jj) * 2 + (int)rank;
  const int mm = cc * 2 + (int)rank;

#define LOAD_EPOCH() const unsigned epoch = ld_relaxed(&g_flags.epoch.v), ep1 = epoch + 1; (void)epoch
  int budget = 1 << 22;

  if (cta >= 0) {
    if (warp >= 8 && warp < 8 + EARLY && elect_one()) {
      const int u = warp - 8;
      const uint32_t fb = bar_full + u * 8;
      mbar_init(fb, 1);
      asm volatile("fence.mbarrier_init.release.cluster;" ::: "memory");
      fence_proxy_async_smem();
      mbar_expect_tx(fb, u < 2 ? QST + SLOT : QST);
      if (u < 2) tma_load_2d(sbase + OFF_S + u * SLOT, &tm_x0, fb, jj * 128 + u * 64, mm * 128);
#pragma unroll
      for (int i = 0; i < 6; i++) tma_load_2d(sbase + u * QST + i * 4096, &tm_wqA, fb, jj * 128 + (u >> 1) * 64 + (i >> 1) * 1024, jj * 128 + (u & 1) * 64 + (i & 1) * 32);
      if (u == 0) PROFT(472);
    }
    __syncwarp();
    {
      const int tx = threadIdx.x;
      const __nv_bfloat16* pf = (tx < 128) ? prm.x0 + (size_t)(mm * 128 + tx) * D_MODEL + jj * 128
                                           : prm.wA_qkv + (size_t)(jj * 128 + (tx & 63)) * 3072 + ((tx - 128) >> 6) * 1024 + jj * 128 + rank * 64;
      if (tx < 320) { if (PF0) asm volatile("prefetch.global.L2 [%0];" :: "l"(pf)); }
      else if (tx == 320) prefetch_tmap(&tm_x0);
      else if (tx == 352) prefetch_tmap(&tm_wqA);
      else if (tx == 383) asm volatile("prefetch.global.L2 [%0];" :: "l"(&g_flags.epoch.v));
    }
    if (elect_one()) {
#pragma unroll
      for (int i = 0; i < 4; i++) {
        const int u = warp * 4 + i;
        if (u >= EARLY) mbar_init(bar_full + u * 8, ((u >= 4 && u < 11) || (u > 32 && u != 40)) ? 2 : 1); mbar_init(bar_done + u * 8, 16);
      }
      mbar_init(bar_stat + warp * 16, 0x111111181182ull >> (4 * warp) & 15);
      mbar_init(bar_stat + warp * 16 + 8, 0x111111121811ull >> (4 * warp) & 15);
      mbar_init(bar_chk + 112 + (warp & 7) * 8, 1);
      asm volatile("fence.mbarrier_init.release.cluster;" ::: "memory");
    }
    __syncthreads();
    asm volatile("barrier.cluster.arrive.relaxed.aligned;" ::: "memory");
  }

  if (cta < 0) {
    LOAD_EPOCH();
    const uint32_t buf = sbase + warp * SLOT, bar = sbase + OFF_BAR + warp * 16;
    const uint32_t lsw = (lane & 7) << 4, lhi = (lane >> 4) << 4, lrow = (lane & 15) * 128;
    const bool el = elect_one();
    if (el) {
      mbar_init(bar, 1); mbar_init(bar + 8, 1);
      asm volatile("fence.mbarrier_init.release.cluster;" ::: "memory");
    }
#pragma unroll 1
    for (int rd = 0; rd < (NLAYERS > 1 ? 5 : 2); rd++) {
      if (rd >= 2 && warp >= 8) break;
      const int tk = rd < 2 ? aux * 12 + warp : aux * 8 + warp;
      const int half = tk & 1;
      const int blk = rd < 2 ? (tk >> 1) * 2 + rd : (4 - rd) * 16 + (tk >> 1);
      const CUtensorMap* tm = rd < 2 ? &tm_wqA : (rd == 2 ? &tm_wqB : &tm_wf);
      const int j0 = (blk & 15) >> 1;
#define AUX_LOAD(n) { const uint32_t d_ = buf + ((n) & 1) * 8192, b_ = bar + ((n) & 1) * 8; const int r_ = kslice(j0, 2 * (n) + half) * 64; \
        mbar_expect_tx(b_, 8192); tma_load_2d(d_, tm, b_, blk * 64, r_); tma_load_2d(d_ + 4096, tm, b_, blk * 64, r_ + 32); }
      if (el) {
        if (rd == 3) { wait_flag(&g_flags.wfready[j0].v, ep1 * 16); fence_proxy_async_global(); }
        AUX_LOAD(0); AUX_LOAD(1);
      }
      __syncwarp();
      float cs[8][4];
#pragma unroll
      for (int i = 0; i < 8; i++) cs[i][0] = cs[i][1] = cs[i][2] = cs[i][3] = 0.f;
#pragma unroll 1
      for (int n = 0; n < 8; n++) {
        const uint32_t tb = buf + (n & 1) * 8192 + lrow;
        mbar_wait(bar + (n & 1) * 8, (n >> 1) & 1);
#pragma unroll
        for (int i = 0; i < 16; i++) {
          uint32_t b0, b1, b2, b3;
          ldsm_x4_t(tb + (i >> 2) * 2048 + (((i & 3) * 32 + lhi) ^ lsw), b0, b1, b2, b3);
          mma_bf16(cs[2 * (i & 3)], 0x3F803F80u, 0x3F803F80u, 0x3F803F80u, 0x3F803F80u, b0, b1);
          mma_bf16(cs[2 * (i & 3) + 1], 0x3F803F80u, 0x3F803F80u, 0x3F803F80u, 0x3F803F80u, b2, b3);
        }
        __syncwarp();
        if (el && n < 6) AUX_LOAD(n + 2);
        __syncwarp();
      }
      if (lane < 4) {
#pragma unroll
        for (int i = 0; i < 8; i++) st_b64(&g_colsum[rd >= 2][blk * 32 + i * 4 + lane][half], __float_as_uint(cs[i][0]), (__float_as_uint(cs[i][1]) & ~3u) | (ep1 & 3));
      }
      __syncwarp();
    }
  } else if (warp >= 8) {
    asm volatile("setmaxnreg.dec.sync.aligned.u32 40;");
    if (warp == 8) {
      const bool el = elect_one();
      cluster_wait();
      if (el) {
#pragma unroll 1
        for (int l = 0; l < NLAYERS; l++) {
          const uint32_t par = l & 1;
          const CUtensorMap* tqk = par ? &tm_wf : &tm_wqA;
          const CUtensorMap* tv = par ? &tm_wqB : &tm_wqA;
          const CUtensorMap* two = par ? &tm_woB : &tm_woA;
          if (l == 1) { LOAD_EPOCH(); wait_flag(&g_flags.wfready[jj].v, ep1 * 16); fence_proxy_async_global(); }
#pragma unroll 1
          for (int u = l ? 0 : EARLY; u < 32; u++) {
            if (u >= 4) mbar_wait_sl(bar_done + (u - 4) * 8, par);
            else if (l) mbar_wait_sl(bar_done + (43 + u + (u >> 1)) * 8, par ^ 1);
            else if (u == 1) __nanosleep(STAG1);
            else if (u == 2 && !W23) mbar_wait_sl(bar_full, 0);
            const uint32_t fb = bar_full + u * 8;
            const bool res = u < 4 ? (l || u >= 2) : (u < 11 || (u >= 18 && u < 22));
            mbar_expect_tx(fb, res ? QST : QST + SLOT);
            const int row = kslice(jj, u < 4 ? u & 1 : (u < 18 ? u - 2 : (u < 22 ? u - 6 : u - 20))) * 64 + (int)rank * 32;
            const int ps = u < 4 ? u >> 1 : (u >= 18), col = jj * 128 + ps * 64;
            const int c0 = par ? jj * 128 + (ps ? 0 : 1024) : col;
            const uint32_t dst = sbase + (u & 3) * QST + rank * 4096;
            tma_load_2d_mc(dst, tqk, fb, c0, row);
            tma_load_2d_mc(dst + 8192, tqk, fb, c0 + (par ? 64 : 1024), row);
            tma_load_2d_mc(dst + 16384, tv, fb, col + 2048, row);
            if (l == PRL && u >= PRU && u < PRU + 4) PROFT(473 + u - PRU);
          }
#pragma unroll 1
          for (int s = 0; s < 16; s++) {
            if (s < 5) { if (s != 2 && s != 4) mbar_wait_sl(bar_done + (28 + s) * 8, par); }
            else if (s != 14) mbar_wait_sl(bar_done + (27 + s - (s == 15)) * 8, par);
            const uint32_t fb = bar_full + (32 + s) * 8;
            mbar_expect_tx(fb, SLOT);
            tma_load_2d_mc(sbase + rank * 8192 + (uint32_t)((WO_BSLOT >> (4 * s)) & 15) * SLOT, two, fb, jj * 128 + (int)rank * 64, wslice(jj, s) * 64);
            const int ts = s + par;
            if (s >= 5 && ts < 8) {
              mbar_expect_tx(bar_chk - 8 + ts * 8, SLOT);
              tma_load_2d(sbase + (uint32_t)((WO_ASLOT(par) >> (4 * ts)) & 15) * SLOT, &tm_o, bar_chk - 8 + ts * 8, wslice(jj, ts) * 64, mm * 128);
            }
          }
        }
      }
      __syncwarp();
    } else if (warp == 9) {
      const bool el = elect_one();
      if (el) {
        if (!EARLY) { PROFT(472); tma_load_2d(sbase + OFF_S, &tm_x0, bar_full, jj * 128, mm * 128); }
        if (EARLY < 2) { __nanosleep(STAG1); tma_load_2d(sbase + OFF_S + SLOT, &tm_x0, bar_full + 8, jj * 128 + 64, mm * 128); }
      }
      __syncwarp();
      LOAD_EPOCH();
#pragma unroll 1
      for (int lp = 0; lp < 4 * NLAYERS; lp++) {
        const int l = lp >> 2, ph = lp & 3;
        if (ph == 3) continue;
        const uint32_t par = l & 1;
        const unsigned* pp = reinterpret_cast<const unsigned*>(g_obuf + (ph >> 1) * 64 + (size_t)(mm * 128 + (ph ? 0 : S_LEN) + (lane & 7) * 16 + (jj & 1) * 8) * D_MODEL +
                                                               (jj >> 1) * 16 + srcb(jj, lane >> 3) * 128);
        const CUtensorMap* tm = lp ? &tm_o : &tm_x0;
        const int row = mm * 128 + ((ph || !l) ? 0 : S_LEN);
        const uint32_t bit = ph ? O_BIT(l) : X_BIT(l - 1);
        const uint32_t slots = ph ? (uint32_t)(WO_ASLOT(par) >> (ph * 32 - 28)) : 0x8769876u;
        const unsigned long long fr = ph == 0 ? XPACE : ph == 1 ? (par ? 0x353535351Full : 0x35351F1Eull) : (par ? 0x27262524232232ull : 0x27262524233232ull);
        uint32_t no = (lp == 0 || (lp & 7) == 1) ? 0 : ~0u, v0 = 0, v1 = 0;
        if (lp || !AX) mbar_wait_sl(ph ? bar_done + ((uint32_t)fr & 63) * 8 : (l ? bar_done + 47 * 8 : bar_full), ph ? par : (l ? par ^ 1 : 0));
        if (el && ph) PROFT(324 + l * 16 + ph);
        __syncwarp();
        if (no) { v0 = ld_relaxed(pp); __nanosleep(POLLGAP); v1 = ld_relaxed(pp); }
#pragma unroll 1
        for (int i = 0; i < (ph == 1 ? 4 + par : 7); i++, no >>= 8) {
#pragma unroll 1
          for (int it = 0; (no & 0xFF) && it < (1 << 18); it++) {
            no &= __ballot_sync(0xffffffffu, (v0 ^ bit) & 1) >> (8 * i);
            if (no) v0 = ld_relaxed(pp);
            if (!(no & 0xFF)) break;
            no &= __ballot_sync(0xffffffffu, (v1 ^ bit) & 1) >> (8 * i);
            if (no) v1 = ld_relaxed(pp);
          }
          if (ph || i >= XP0) mbar_wait_sl(bar_done + ((uint32_t)(fr >> (8 * i)) & 63) * 8, par);
          if (el) {
            if (i == 0) PROFT(320 + l * 16 + ph);
            const uint32_t cb = bar_chk + (ph >> 1) * 112 + i * 8;
            mbar_expect_tx(cb, SLOT);
            tma_load_2d(sbase + ((slots >> (4 * i)) & 15) * SLOT, tm, cb, srcb(jj, i) * 128 + (ph >> 1) * 64, row);
          }
          __syncwarp();
        }
        if (ph == 0 && el) {
          if (l) { wait_flag(&g_flags.xready[l][mm].v, ep1 * 8); fence_proxy_async_global(); }
#pragma unroll 1
          for (int u = 11; u < 34; u++) {
            if (u == 18) u = 22;
            mbar_wait_sl(bar_done + (u - 4) * 8, par);
            if (u == 32) mbar_expect_tx(bar_xr, 2 * SLOT);
            tma_load_2d(sbase + OFF_RA + (u & 3) * SLOT, tm, u < 32 ? bar_full + u * 8 : bar_xr, kslice(jj, u < 18 ? u - 2 : (u < 32 ? u - 20 : u - 32)) * 64, row);
          }
        }
        __syncwarp();
      }
      cluster_wait();
    } else {
      const int hw = warp - 10;
      LOAD_EPOCH();
      const bool el = elect_one();
      cluster_wait();
      if (hw == 0) {
        mbar_wait_sl(bar_full + 8, 0);
        if (lane < 7) prefetch_tmap(lane == 0 ? &tm_os : lane == 1 ? &tm_o : lane == 2 ? &tm_wf : lane == 3 ? &tm_wqB : lane == 4 ? &tm_woA : lane == 5 ? &tm_woB : &tm_phi);
#pragma unroll 1
        for (int i = 0; i < (NLAYERS > 1 ? 9 : 0); i++) {
          if (i == 0 || i == 5) mbar_wait_sl(bar_done + (i >> 1) * 12, 0);
          if (el) {
            if (i == 0) { mbar_expect_tx(bar_phi, 2 * SLOT + 8192); tma_load_2d(sbase + OFF_PHI, &tm_phi, bar_phi, 0, jj * 128); }
            else tma_load_2d(sbase + (i > 4 ? 10 : 12) * SLOT - 4096 + i * 4096, &tm_wqB, bar_phi, (i > 4 ? 896 : 0) + jj * 128 + ((i - 1) >> 1) * 64, mm * 64 + (~i & 1) * 32);
          }
          __syncwarp();
          __nanosleep(PFGAP);
        }
      } else {
#pragma unroll 1
        for (int b = 0; b < 2; b++) {
          float4* z = reinterpret_cast<float4*>(g_kv[b] + (jj * 4) * KVH + mm * (4 * KVH / 16)) + lane;
#pragma unroll
          for (int i = 0; i < 6; i++) z[i * 32] = make_float4(0.f, 0.f, 0.f, 0.f);
        }
#pragma unroll 1
        for (int i = 0; i < 16; i++) {
          const int b = i >> 2;
          const uint32_t v = (b == 0 ? O_BIT(0) : b == 1 ? X_BIT(0) : H_BIT(0)) + 1;
          uint4* p = b < 2 ? reinterpret_cast<uint4*>(g_obuf + (size_t)(b * S_LEN + mm * 128 + (i & 3) * 32 + (lane >> 3) * 8) * D_MODEL + jj * 128 + (b ? 0 : 64)) + (lane & 7)
                           : g_halo + (size_t)(mm * 8 + jj) * 512 + i * 32 + lane;
          *p = make_uint4(v, v, v, v);
        }
        fence_proxy_async_global();
      }
      __syncwarp();
      uint32_t chkp = 0;
#pragma unroll 1
      for (int lp = 0; lp < 4 * NLAYERS; lp++) {
        const int l = lp >> 2, ph = (lp & 3) == 2 ? 2 - hw : (lp & 3);
        const uint32_t par = l & 1;
        int lane; asm volatile("mov.u32 %0, %%laneid;" : "=r"(lane));
        if ((lp & 3) == 2 || (hw && ph == 0)) {
          const uint32_t bit = ph ? O_BIT(l) : X_BIT(l - 1);
          uint32_t slots = ph ? (uint32_t)(WO_ASLOT(par) >> (ph * 32 - 28)) : 0x8769876u;
          const uint32_t a0 = sbase + (lane & 7) * 132 + (lane >> 3) * 32;
#pragma unroll 1
          for (int c = 0; c < 7; c++, slots >>= 4) {
            const uint32_t cb = bar_chk + 112 - hw * 112 + c * 8;
#pragma unroll 1
            for (int it = 0; it < (1 << 12); it++) {
              mbar_wait_sl(cb, (chkp >> c) & 1);
              chkp ^= 1u << c;
              if (el && c == 0) PROFT(ph == 1 ? 480 + l * 2 : 488 + l * 2 + (ph >> 1));
              if (lp == 0) break;
              uint32_t bad;
              asm volatile("{\n.reg .b32 w<16>;\n"
                           "ld.shared.u32 w0, [%1 + 0];\n"
                           "ld.shared.u32 w1, [%1 + 1024];\n"
                           "ld.shared.u32 w2, [%1 + 2048];\n"
                           "ld.shared.u32 w3, [%1 + 3072];\n"
                           "ld.shared.u32 w4, [%1 + 4096];\n"
                           "ld.shared.u32 w5, [%1 + 5120];\n"
                           "ld.shared.u32 w6, [%1 + 6144];\n"
                           "ld.shared.u32 w7, [%1 + 7168];\n"
                           "ld.shared.u32 w8, [%1 + 8192];\n"
                           "ld.shared.u32 w9, [%1 + 9216];\n"
                           "ld.shared.u32 w10, [%1 + 10240];\n"
                           "ld.shared.u32 w11, [%1 + 11264];\n"
                           "ld.shared.u32 w12, [%1 + 12288];\n"
                           "ld.shared.u32 w13, [%1 + 13312];\n"
                           "ld.shared.u32 w14, [%1 + 14336];\n"
                           "ld.shared.u32 w15, [%1 + 15360];\n"
                           "lop3.b32 w0, w0, w1, %2, 0x7E;\n"
                           "lop3.b32 w2, w2, w3, %2, 0x7E;\n"
                           "lop3.b32 w4, w4, w5, %2, 0x7E;\n"
                           "lop3.b32 w6, w6, w7, %2, 0x7E;\n"
                           "lop3.b32 w8, w8, w9, %2, 0x7E;\n"
                           "lop3.b32 w10, w10, w11, %2, 0x7E;\n"
                           "lop3.b32 w12, w12, w13, %2, 0x7E;\n"
                           "lop3.b32 w14, w14, w15, %2, 0x7E;\n"
                           "lop3.b32 w0, w0, w2, w4, 0xFE;\nlop3.b32 w6, w6, w8, w10, 0xFE;\nlop3.b32 w0, w0, w12, w14, 0xFE;\nlop3.b32 %0, w0, w6, 1, 0xA8;\n}\n"
                           : "=r"(bad) : "r"(a0 + (slots & 15) * SLOT), "r"(bit) : "memory");
              if (__all_sync(0xffffffffu, bad == 0)) break;
              if (el) {
                fence_proxy_async_smem();
                mbar_expect_tx(cb, SLOT);
                tma_load_2d(sbase + (slots & 15) * SLOT, &tm_o, cb, srcb(jj, c) * 128 + (ph >> 1) * 64, mm * 128 + (ph ? 0 : S_LEN));
                RETRY_COUNT();
              }
              __syncwarp();
            }
            if (el) { mbar_arrive_local(bar_full + (c + (ph ? 25 + ph * 8 : 4)) * 8); if (lp == PRL * 4 && c == 0) PROFT(477); }
            __syncwarp();
          }
          if (ph) continue;
#pragma unroll 1
          for (int hp = 0; hp < 2; hp++) {
            const uint4* src = reinterpret_cast<const uint4*>(g_colsum[par][jj * 64 + hp * 32 + lane]);
            uint32_t bad;
            int it = 0;
            float c[6];
            do {
              bad = 0;
#pragma unroll
              for (int p = 0; p < 3; p++) {
                const uint4 v = ld_ll(src + ((par && p < 2) ? (hp ? -32 : 512) + p * 32 : p * 512));
                bad |= (v.y ^ ep1) | (v.w ^ ep1);
                c[2 * p] = __uint_as_float(v.x) + __uint_as_float(v.z); c[2 * p + 1] = __uint_as_float(v.y) + __uint_as_float(v.w);
              }
              bad &= 3;
              if (bad) __nanosleep(300);
            } while (bad && ++it < (1 << 16));
#pragma unroll
            for (int p = 0; p < 6; p++) {
              uint32_t h, m, lo;
              split3(c[p], h, m, lo);
              sts128(sbase + OFF_LNB + hp * 4096 + (p >> 1) * 1024 + lane * 32 + (p & 1) * 16, h | (m << 16), h | (lo << 16), h | (m << 16), lo | (m << 16));
            }
            fence_proxy_async_smem();
            __syncwarp();
            if (el) { mbar_arrive_local(hp ? bar_stat2 : bar_stat); if (hp == 0) PROFT(324 + l * 16); }
            __syncwarp();
          }
          continue;
        } else if (ph == 0) {
          mbar_wait_sl(bar_done + 24, par);
          const uint4* sp = reinterpret_cast<const uint4*>(g_stats + (size_t)(mm * 128) * 8) + lane;
#pragma unroll 1
          for (int hf = 0; hf < 4; hf++) {
            uint4 v[4];
            uint32_t bad;
            int it = 0;
            do {
              bad = 0;
#pragma unroll
              for (int i = 0; i < 4; i++) { v[i] = ld_ll(sp + (hf * 4 + i) * 32); bad |= (v[i].y ^ STAT_TAG(l)) | (v[i].w ^ STAT_TAG(l)); }
              bad &= 3;
              if (bad) __nanosleep(200);
            } while (bad && ++it < (1 << 16));
            __syncwarp();
            float mean = 0.f, m2 = 0.f;
#pragma unroll
            for (int i = 0; i < 4; i++) {
              float a = __uint_as_float(v[i].x) + __uint_as_float(v[i].z);
              a += __shfl_xor_sync(0xffffffffu, a, 1); a += __shfl_xor_sync(0xffffffffu, a, 2);
              a *= 0.125f;
              const float e0 = __uint_as_float(v[i].x) - a, e1 = __uint_as_float(v[i].z) - a;
              float q = fmaf(fmaf(e0, e0, e1 * e1), 128.f, __uint_as_float(v[i].y) + __uint_as_float(v[i].w));
              q += __shfl_xor_sync(0xffffffffu, q, 1); q += __shfl_xor_sync(0xffffffffu, q, 2);
              if ((lane & 3) == i) { mean = a; m2 = q; }
            }
            const uint32_t row = hf * 32 + (lane & 3) * 8 + (lane >> 2);
            uint32_t h, m, lo;
            split3(-0.5f * mean, h, m, lo);
            sts128(sbase + OFF_LNA + row * 16, h | (h << 16), m | (h << 16), lo | (m << 16), m | (lo << 16));
            sts32f(sbase + OFF_ST + row * 4, rsqrtf(m2 * (1.f / 1024.f) + 1e-5f));
          }
          fence_proxy_async_smem();
          __syncwarp();
          if (el) { mbar_arrive_local(bar_stat); PROFT(323 + l * 16); }
          __syncwarp();
#pragma unroll 1
          for (int i = 0; i < 8 - 4 * l; i++) {
            asm volatile("prefetch.global.L2 [%0];" :: "l"(i < 4 ? (l ? prm.wB_o : prm.wA_o) + (size_t)cta * 8192 + i * 2048 + lane * 64
                                                                 : prm.wB_qkv + (size_t)(cta * 8 + (i - 4) * 2 + (lane >> 4)) * 3072 + 2048 + (lane & 15) * 64));
            __nanosleep(PFGAP);
          }
          continue;
        }
        if (ph == 1) {
          if (par) continue;
#pragma unroll 1
          for (int i = 0; i < 2; i++) {
            if (i && lp + hw == 1 && NLAYERS > 1) {
#pragma unroll 1
              for (int c = 0; c < 8; c++) {
                if (!(c & 3)) asm volatile("bar.sync %0, 288;" :: "r"(BAR_WF + (c >> 2)) : "memory");
                if (el) {
                  tma_store_2d(&tm_wf, sbase + 11 * SLOT + c * 4096, (c < 4 ? 1024 : -128) + jj * 128 + (c >> 1) * 64, mm * 64 + (c & 1) * 32);
                  if ((c & 3) == 3) {
                    asm volatile("cp.async.bulk.commit_group;\ncp.async.bulk.wait_group.read 0;" ::: "memory");
                    mbar_arrive_local(bar_phi + (c >> 2) * 8);
                  } else __nanosleep(WFGAP);
                }
                __syncwarp();
              }
              if (el) { bulk_commit_wait(); signal_release(&g_flags.wfready[jj].v); PROFT(335); }
              __syncwarp();
            }
            mbar_wait_sl(bar_done + (i ? HW1 : (hw ? 19 : HW0)) * 8, 0);
            if (lp + hw == 2 && NLAYERS > 1) mbar_wait_sl(bar_phi, 1);
            const uint4* src = g_halo + (size_t)(mm * 8 + jj - 8) * 512 + i * 256 + hw * 128 + lane;
            uint4 v[4];
            int it = 0;
            bool ok;
            do {
#pragma unroll
              for (int j = 0; j < 4; j++) v[j] = mm ? ld_b128(src + j * 32) : make_uint4(H_BIT(l), 0, 0, 0);
              ok = __all_sync(0xffffffffu, (((v[0].x ^ H_BIT(l)) | (v[1].x ^ H_BIT(l)) | (v[2].x ^ H_BIT(l)) | (v[3].x ^ H_BIT(l))) & 1) == 0);
            } while (!ok && ++it < (1 << 16));
#pragma unroll
            for (int j = 0; j < 4; j++) sts128(sbase + OFF_S + hw * SLOT + j * 512 + lane * 16, v[j].x, v[j].y, v[j].z, v[j].w);
            __syncwarp();
            if (el) { mbar_arrive_local(bar_halo + hw * 8); PROFT(331 + l * 16 + i * 2 + hw); }
            __syncwarp();
          }
        } else if (hw == 0 && l < NLAYERS - 1) {
          bar_sync<BAR_X1, 288>();
          if (el) {
            PROFT(328 + l * 16);
            mbar_wait_sl(bar_full + XD * 8, par ^ 1);
            tma_store_2d(&tm_o, sbase + 11 * SLOT, jj * 128 + 64, mm * 128 + S_LEN);
            bulk_commit_wait();
            signal_release(&g_flags.xready[l + 1][mm].v);
            PROFT(330 + l * 16);
          }
          __syncwarp();
        }
      }
    }
    cluster_sync();
  } else {
    asm volatile("setmaxnreg.inc.sync.aligned.u32 232;");
    LOAD_EPOCH();
    const int wg = warp >> 2;
    const int r0 = warp * 16;
    const uint32_t pK = sbase + OFF_S, pV = sbase + OFF_S + SLOT;
#define PMASKS(on, bit) const uint32_t pm0 = ((on) && t == (g & 3) && (g >> 2) == (g & 1)), pm1 = ((on) && t == (g & 3) && (g >> 2) != (g & 1)), pbit = (bit)
#define PBIT0(w) (((w) & ~pm0) | (pbit & pm0))
#define PBIT1(w) (((w) & ~pm1) | (pbit & pm1))
#define LANE_CONSTS() \
    int lane; asm volatile("mov.u32 %0, %%laneid;" : "=r"(lane)); \
    const int g = lane >> 2, t = lane & 3; \
    const uint32_t srowoff = (r0 + (lane & 15)) * 128, lsw = (lane & 7) << 4, lhi = (lane >> 4) << 4, lsw2 = (lane & 6) << 3; \
    (void)g; (void)t; (void)srowoff; (void)lsw; (void)lhi; (void)lsw2;
    uint32_t stgp = 0, peer;
    asm volatile("mapa.shared::cluster.u32 %0, %1, %2;" : "=r"(peer) : "r"(sbase), "r"(rank ^ 1));
    peer -= sbase;
    const uint32_t dA0 = (((sbase & 0x3FFFF) + wg * 8192) >> 4) | 0x10000u, dB0 = ((sbase & 0x3FFFF) >> 4) | 0x2000000u;
    cluster_wait();
#define DESC(lo, hi) ((uint64_t)(uint32_t)(lo) | ((uint64_t)(hi) << 32))
#define STG_ARRIVE() { __syncwarp(); if (elect_one()) mbar_arrive_local(bar_stg); }
#define STG_WAIT() { mbar_wait(bar_stg, stgp); stgp ^= 1; }
#define PROFS() do {} while (0)
#define REL(addr) { if (elect_one()) { mbar_arrive_local(addr); asm volatile("mbarrier.arrive.shared::cluster.b64 _, [%0];" :: "r"((addr) + peer) : "memory"); } }
#define QSTEP(ACC, DA, SC, PRE) { \
      const uint32_t da = (DA), db = dB0 + (ub & 0x18) * (QST >> 7); \
      mbar_wait(ub, par); \
      PRE; \
      wgmma_fence(); \
      wgmma4_n192<SC>(ACC, da, db); \
      wgmma_commit(); PROFS(); }
#define QREL() { wgmma_wait<1>(); REL(ub + 376); ub += 8; }
#define RA_CUR (dA0 + (OFF_RA >> 4) + (ub & 0x18) * (SLOT >> 7))
#define PUMP1() { QSTEP(S1, RA_CUR, 1, {}); QREL(); }
#define PUMP0() { PUMP1(); SCHED_FENCE(); }
#define PUMP() if (h == 0) PUMP1()
#define WSTEP() { \
      const uint32_t s4 = (ub - bar_full - 256) >> 1; \
      const uint32_t da = dA0 + (((uint32_t)(WO_ASLOT(par) >> s4) & 15) << 10), db = dB0 + (((uint32_t)(WO_BSLOT >> s4) & 15) << 10); \
      mbar_wait(ub, par); \
      wgmma_fence(); \
      wgmma4_n128<1>(S1, da, db); \
      wgmma_commit(); PROFS(); \
      wgmma_wait<1>(); \
      if (s4) REL(ub + 376); \
      ub += 8; }
#define PUMPS(n) { _Pragma("unroll 1") for (int i_ = 0; i_ < (n); i_++) PUMP1(); }
#define SITE(n) { if ((BMASK >> (n)) & 1) PUMP1(); SCHED_FENCE(); }
#define LNSTEP(ACC, hh) { wgmma_fence(); wgmma_n192<1, 0>(ACC, make_desc(sbase + OFF_LNA + wg * 1024, 0, 128) ^ (1ull << 62), make_desc(sbase + OFF_LNB + (hh) * 4096, 0, 128) ^ (1ull << 62)); }
#define DRAIN_B(ACC) { \
      LANE_CONSTS(); \
      STAGE_V(ACC + 64, pV); \
      _Pragma("unroll") for (int i_ = 0; i_ < 64; i_++) st[i_] = ACC[i_]; \
      PIN(st, 64); }
#define WARP_STORE(tm, tile, col, row) { fence_proxy_async_smem(); __syncwarp(); \
      if (elect_one()) { tma_store_2d(tm, (tile) + r0 * 128, col, (row) + r0); asm volatile("cp.async.bulk.commit_group;" ::: "memory"); } __syncwarp(); }
#define PUBLISH_O() WARP_STORE(&tm_os, pO, jj * 128 + h * 64, mm * 128)
#define X_OUT(pc, on) { \
      PMASKS(on, X_BIT(l)); \
      _Pragma("unroll") for (int j = (pc) * 4; j < (pc) * 4 + 4; j++) \
        stsm_x4(pK + (pc) * SLOT + srowoff + ((((uint32_t)(j & 3) << 5) + lhi) ^ lsw), \
                PBIT0(pack_bf16(S1[j * 8 + 0], S1[j * 8 + 1])), PBIT0(pack_bf16(S1[j * 8 + 2], S1[j * 8 + 3])), \
                PBIT1(pack_bf16(S1[j * 8 + 4], S1[j * 8 + 5])), PBIT1(pack_bf16(S1[j * 8 + 6], S1[j * 8 + 7]))); }
#define REST_P1(SKEW) { \
      mbar_wait(bar_stat2, par); \
      LNSTEP(S1, 1); \
      _Pragma("unroll 1") while (ub < bar_full + 256) { \
        if (ub == bar_full + 256 - 8 * (SKEW) && wg == 0) bar_sync<BAR_SKEW, 256>(); \
        QSTEP(S1, RA_CUR, 1, {}); \
        if (ub == bar_full + 248 && wg == 1) bar_arrive<BAR_SKEW, 256>(); \
        QREL(); \
      } \
      mbar_wait(bar_done + (31 - (SKEW)) * 8, par);        \
      wgmma_wait<0>(); \
      ACC_FENCE(S1, 96); \
      REL(bar_done + 31 * 8); \
      PROF(13); }
#define FOLD(tile, rd) { \
          LANE_CONSTS(); \
          float d[32]; \
          ACC_DEF(d, 32); \
          mbar_wait(bar_phi, 0); \
          wgmma_fence(); \
          _Pragma("unroll") for (int i = 0; i < 2; i++) { \
            const uint64_t da = make_desc((tile) + wg * 8192 + i * 64, 16, 1024); \
            const uint64_t db = make_desc(sbase + OFF_PHI + wg * 4096 + i * 2048, 16, 512) ^ (3ull << 62); \
            wgmma_n32<0>(d + i * 16, da, db); wgmma_n32<1>(d + i * 16, da + 2, db + 64); \
          } \
          wgmma_commit(); \
          PUMP0(); \
          ACC_FENCE(d, 32); \
          bar_wg(wg); \
          _Pragma("unroll") for (int i = 0; i < 4; i++) { \
            const float* x = d + (i & 1) * 8 + (i >> 1) * 2; \
            if (rd) sts128((tile) + wg * 8192 + ((warp & 3) * 16 + (i >> 1) * 8 + g) * 128 + (((2 * t + (i & 1)) ^ g) << 4), \
                           pack_bf16(x[0], x[1]), pack_bf16(x[4], x[5]), pack_bf16(x[16], x[17]), pack_bf16(x[20], x[21])); \
            else stsm_x4((tile) + srowoff + ((((uint32_t)i << 5) + lhi) ^ lsw), pack_bf16(d[i * 8], d[i * 8 + 1]), pack_bf16(d[i * 8 + 2], d[i * 8 + 3]), \
                         pack_bf16(d[i * 8 + 4], d[i * 8 + 5]), pack_bf16(d[i * 8 + 6], d[i * 8 + 7])); \
          } \
          }
#define LOAD_X0(base) \
      _Pragma("unroll") for (int j = 0; j < 8; j++) { \
        uint32_t x0, x1, x2, x3; \
        ldsm_x4((base) + (j >> 2) * SLOT + srowoff + ((((uint32_t)(j & 3) << 5) + lhi) ^ lsw), x0, x1, x2, x3); \
        S1[j * 8 + 0] = bf_lo(x0); S1[j * 8 + 1] = bf_hi(x0); S1[j * 8 + 2] = bf_lo(x1); S1[j * 8 + 3] = bf_hi(x1); \
        S1[j * 8 + 4] = bf_lo(x2); S1[j * 8 + 5] = bf_hi(x2); S1[j * 8 + 6] = bf_lo(x3); S1[j * 8 + 7] = bf_hi(x3); \
      }
#define LOAD_X() { \
      wgmma_wait<0>(); \
      mbar_wait(bar_xr, par); \
      LOAD_X0(sbase + OFF_RA); \
      ACC_FENCE(S1, 64); \
      __syncwarp(); if (elect_one()) mbar_arrive_local(bar_lx); }

    float S1[96];
#pragma unroll
    for (int i = 0; i < 64; i++) S1[i] = 0.f;
#pragma unroll 1
    for (int l = 0; l < NLAYERS; l++) {
      const uint32_t par = l & 1;
      bar_wg(wg);
      PROF(0);
      uint32_t ub = bar_full;
      float S0[96];
      {
        LANE_CONSTS();
        ACC_DEF(S0, 96);
        QSTEP(S0, dA0 + (OFF_S >> 4), 0, {});
        ub += 8;
        PROF(1);
        if (l == 0) { mbar_wait(ub, 0); LOAD_X0(pK); }
        else { X_OUT(1, false); fence_proxy_async_smem(); }
        SCHED_FENCE();
        {
          float a0 = S1[0], a1 = S1[2], b0 = S1[1], b1 = S1[3];
#pragma unroll
          for (int i = 4; i < 64; i += 4) { a0 += S1[i]; b0 += S1[i + 1]; a1 += S1[i + 2]; b1 += S1[i + 3]; }
          a0 += b0; a1 += b1;
          a0 += __shfl_xor_sync(0xffffffffu, a0, 1); a1 += __shfl_xor_sync(0xffffffffu, a1, 1);
          a0 += __shfl_xor_sync(0xffffffffu, a0, 2); a1 += __shfl_xor_sync(0xffffffffu, a1, 2);
          a0 *= (1.f / 128.f); a1 *= (1.f / 128.f);
          asm volatile("" : "+f"(a0), "+f"(a1));
          bar_wg(wg);
          QSTEP(S0, dA0 + ((OFF_S + SLOT) >> 4), 1, wgmma_wait<0>());
          REL(ub + 376); ub += 8;
          SCHED_FENCE();
          float q0 = 0.f, q1 = 0.f;
          b0 = 0.f; b1 = 0.f;
#pragma unroll
          for (int i = 0; i < 64; i += 4) {
            const float d0 = S1[i] - a0, d1 = S1[i + 1] - a0, d2 = S1[i + 2] - a1, d3 = S1[i + 3] - a1;
            q0 = fmaf(d0, d0, q0); b0 = fmaf(d1, d1, b0); q1 = fmaf(d2, d2, q1); b1 = fmaf(d3, d3, b1);
          }
          q0 += b0; q1 += b1;
          q0 += __shfl_xor_sync(0xffffffffu, q0, 1); q1 += __shfl_xor_sync(0xffffffffu, q1, 1);
          q0 += __shfl_xor_sync(0xffffffffu, q0, 2); q1 += __shfl_xor_sync(0xffffffffu, q1, 2);
          if (t < 2) st_b64(g_stats + (size_t)(mm * 128 + r0 + g + t * 8) * 8 + jj, __float_as_uint(t ? a1 : a0), (__float_as_uint(t ? q1 : q0) & ~3u) | STAT_TAG(l));
        }
        if (l) { asm volatile("cp.async.bulk.wait_group 0;" ::: "memory"); bar_arrive<BAR_X1, 288>(); }
        ACC_DEF(S1, 96);
        QSTEP(S1, dA0 + (OFF_S >> 4), 0, {});
        QREL();
        QSTEP(S1, dA0 + ((OFF_S + SLOT) >> 4), 1, {});
        QREL();
#pragma unroll 1
        for (int i = 0; i < 14; i++) {
          QSTEP(S0, RA_CUR, 1, {});
          if (i == 0) PROF(2);
          QREL();
        }
      }
      LANE_CONSTS();
      mbar_wait(bar_stat, par);
      LNSTEP(S0, 0);
      wgmma_commit();
      const float rs0 = lds32f(sbase + OFF_ST + (r0 + g) * 4), rs1 = lds32f(sbase + OFF_ST + (r0 + g + 8) * 4);
      PUMP0();
      ACC_FENCE(S0, 96);
      PROF(3);
      if (!par) {
        constexpr uint32_t par = 0;
        uint32_t qa[16];
        uint32_t kf[32], vf[32];
#define DRAIN_A(ACC, hp, PMP) { \
          LANE_CONSTS(); \
          FRAG(kf + 16, ACC + 32, 0, (hp) * 2); \
          PMP; \
          FRAG(vf + 16, ACC + 64, 1, (hp) * 2 + 1); \
          _Pragma("unroll") for (int i_ = 0; i_ < 16; i_++) qa[i_] = pack_bf16(ACC[2 * i_], ACC[2 * i_ + 1]); \
          PINU(qa, 16); }
        DRAIN_A(S0, 0, PUMP0());
        if (l == 0 && NLAYERS > 1) {
#pragma unroll 1
          for (int rd = 1; rd >= 0; rd--) {
            FOLD(sbase + (12 - rd) * SLOT, rd);
            fence_proxy_async_smem();
            asm volatile("bar.arrive %0, 288;" :: "r"(BAR_WF + 1 - rd) : "memory");
          }
        }
        PUMPS(FPUMP);
        if (l == 0 && NLAYERS > 1) mbar_wait(bar_phi, 1);
#pragma unroll 1
        for (int h = 0; h < 2; h++) {
          const uint32_t pO = sbase + (h ? 3 : 12) * SLOT;
          PROF(4 + h * 12);
          LANE_CONSTS();
          FRAG_PUT(kf + 16, 10); FRAG_PUT(vf + 16, 11);
          STG_ARRIVE();
          if (h) { LOAD_X(); if (AW0) WSTEP(); } else PUMPS(HPUMP2);
          STG_WAIT();
          if (warp == 0) mbar_wait(bar_halo, h);
          FRAG_GET(kf, 10);
          PROF(5 + h * 12);
          float s[2][4][4];
#pragma unroll
          for (int ks = 0; ks < 2; ks++)
#pragma unroll
            for (int i = 0; i < 8; i++) {
              const int hh = (i >> 1) & 1, jb = (i & 1) + (~i >> 1 & 2);
              const uint32_t* b = kf + (jb >> 1) * 16 + hh * 8 + ks * 4 + (jb & 1) * 2;
              if (ks) mma_bf16(s[hh][jb], qa[hh * 8 + 4], qa[hh * 8 + 5], qa[hh * 8 + 6], qa[hh * 8 + 7], b[0], b[1]);
              else mma_bf16_z(s[hh][jb], qa[hh * 8], qa[hh * 8 + 1], qa[hh * 8 + 2], qa[hh * 8 + 3], b[0], b[1]);
            }
          PUMP();
          PROF(6 + h * 12);
          const bool e = g & 1, hb = (2 * t + (g & 1)) <= g;
          float va[2][2], vb[2][2], mx[2][2];
#pragma unroll
          for (int hh = 0; hh < 2; hh++) {
            va[hh][0] = e ? s[hh][1][1] : s[hh][1][0];
            vb[hh][0] = hb ? (e ? s[hh][2][1] : s[hh][2][0]) : (e ? s[hh][0][1] : s[hh][0][0]);
            va[hh][1] = e ? s[hh][2][3] : s[hh][2][2];
            vb[hh][1] = hb ? (e ? s[hh][3][3] : s[hh][3][2]) : (e ? s[hh][1][3] : s[hh][1][2]);
          }
          if (warp == 0 && mm == 0) {
#pragma unroll
            for (int hh = 0; hh < 2; hh++) { va[hh][0] = -INFINITY; if (!hb) { vb[hh][0] = -INFINITY; vb[hh][1] = -INFINITY; } }
          }
#pragma unroll
          for (int i = 0; i < 4; i++) mx[i >> 1][i & 1] = fmaxf(va[i >> 1][i & 1], vb[i >> 1][i & 1]);
#pragma unroll
          for (int o = 1; o <= 2; o <<= 1)
#pragma unroll
            for (int i = 0; i < 4; i++) mx[i >> 1][i & 1] = fmaxf(mx[i >> 1][i & 1], __shfl_xor_sync(0xffffffffu, mx[i >> 1][i & 1], o));
          const float sc0 = rs0 * (0.17677669529663687f * LOG2E), sc1 = rs1 * (0.17677669529663687f * LOG2E);
#pragma unroll
          for (int i = 0; i < 4; i++) {
            const float sc = (i & 1) ? sc1 : sc0, m = mx[i >> 1][i & 1];
            va[i >> 1][i & 1] = ex2((va[i >> 1][i & 1] - m) * sc); vb[i >> 1][i & 1] = ex2((vb[i >> 1][i & 1] - m) * sc);
            mx[i >> 1][i & 1] = va[i >> 1][i & 1] + vb[i >> 1][i & 1];
          }
          if (h == 0 && ASITE) { PIN(&va[0][0], 4); PIN(&vb[0][0], 4); PIN(&mx[0][0], 4); PUMP1(); }
          if (warp == 0) mbar_wait(bar_halo + 8, h);
          FRAG_GET(vf, 11);
#pragma unroll
          for (int o = 1; o <= 2; o <<= 1)
#pragma unroll
            for (int i = 0; i < 4; i++) mx[i >> 1][i & 1] += __shfl_xor_sync(0xffffffffu, mx[i >> 1][i & 1], o);
          const uint32_t selA = e ? 0x1044 : 0x4410, selB = e ? 0x3244 : 0x4432, selL = hb ? 0x4444 : selB, selH = hb ? selB : 0x4444;
          float o[2][4][4];
          uint32_t pa[2][8];
#pragma unroll
          for (int hh = 0; hh < 2; hh++) {
            const float i0 = rcp_fast(mx[hh][0]), i1 = rcp_fast(mx[hh][1]);
            const uint32_t w0 = pack_bf16(va[hh][0] * i0, vb[hh][0] * i0), w1 = pack_bf16(va[hh][1] * i1, vb[hh][1] * i1);
            pa[hh][0] = __byte_perm(w0, 0, selL); pa[hh][2] = __byte_perm(w0, 0, selA); pa[hh][3] = __byte_perm(w1, 0, selL);
            pa[hh][4] = __byte_perm(w0, 0, selH); pa[hh][5] = __byte_perm(w1, 0, selA); pa[hh][7] = __byte_perm(w1, 0, selH);
            pa[hh][1] = pa[hh][0] & pa[hh][4]; pa[hh][6] = pa[hh][3] & pa[hh][7];
          }
          PROF(7 + h * 12);
#pragma unroll
          for (int i = 0; i < 8; i++) mma_bf16_z(o[i >> 2][i & 3], pa[i >> 2][4], pa[i >> 2][5], pa[i >> 2][6], pa[i >> 2][7], vf[16 + 2 * i], vf[17 + 2 * i]);
#pragma unroll
          for (int i = 0; i < 8; i++) mma_bf16(o[i >> 2][i & 3], pa[i >> 2][0], pa[i >> 2][1], pa[i >> 2][2], pa[i >> 2][3], vf[2 * i], vf[2 * i + 1]);
          if (h == 0) PUMP1() else mbar_wait(bar_done + 30 * 8, par);
          if (NLAYERS > 1) mbar_wait(bar_phi + 8, 0);
#pragma unroll
          for (int i = 0; i < 4; i++) {
            const int hh = i >> 1, dp = i & 1;
            PMASKS(true, O_BIT(l));
            stsm_x4(pO + srowoff + ((hh * 64 + dp * 32 + lhi) ^ lsw), PBIT0(pack_bf16(o[hh][dp * 2][0], o[hh][dp * 2][1])), PBIT0(pack_bf16(o[hh][dp * 2][2], o[hh][dp * 2][3])),
                    PBIT1(pack_bf16(o[hh][dp * 2 + 1][0], o[hh][dp * 2 + 1][1])), PBIT1(pack_bf16(o[hh][dp * 2 + 1][2], o[hh][dp * 2 + 1][3])));
          }
          PUBLISH_O();
          PROF(11 + h * 12);
          if (h) break;
          REST_P1(ASKEW);
          asm volatile("cp.async.bulk.wait_group.read 0;" ::: "memory");
          DRAIN_A(S1, 1, {});
        }
      } else {
        constexpr uint32_t par = 1;
        float st[64];
        DRAIN_B(S0);
        if (warp < 2) sts128(sbase + OFF_ONES + warp * 512 + lane * 16, 0x3F803F80u, 0x3F803F80u, 0x3F803F80u, 0x3F803F80u);
        const float c0 = rs0 * LOG2E, c1 = rs1 * LOG2E;
#define KV_MMA(vs) { \
          const uint32_t dp = dA0 + 12 * 1024 - wg * 2560, dv = dA0 + (vs) * 1024 + ((OFF_ONES - (vs) * SLOT - 16) << 12) - wg * (512 << 16); \
          STG_WAIT(); \
          wgmma_fence(); \
          _Pragma("unroll") for (int ks = 0; ks < 8; ks++) { \
            const uint64_t a = DESC(dp + ks * 128, 0x40000040), b = DESC(dv + ks * (64 - (64 << 16)), 0x80000020); \
            if (ks == 0) wgmma_n40<0, 1>(kv, a, b); else wgmma_n40<1, 1>(kv, a, b); } \
          wgmma_commit(); }
#define KV_RED(hp) { \
          float* kvg = g_kv[l >> 1] + (jj * 4 + (hp) * 2) * KVH + warp * 768 + lane * 4; \
          _Pragma("unroll") for (int i = 0; i < 5; i++) red_v4(kvg + i * 128, kv[i * 3], kv[i * 3 + 1], kv[i * 3 + 2], 1.f); \
          red_v4(kvg + 640, kv[15], kv[16], kv[18], 1.f); }
#define KV_LOAD(hp) { \
          const uint4* kvg = reinterpret_cast<const uint4*>(g_kv[l >> 1] + (jj * 4 + (hp) * 2) * KVH) + warp * 192 + lane; \
          _Pragma("unroll") for (int i = 0; i < 6; i++) v[i] = ld_b128(kvg + i * 32); }
#define KVV(i) __uint_as_float((i) % 3 == 0 ? v[(i) / 3].x : ((i) % 3 == 1 ? v[(i) / 3].y : v[(i) / 3].z))
#define KV_TILE(hp) { \
          _Pragma("unroll 1") for (int it = 0; it < (1 << 16); it++) { \
            if (__all_sync(0xffffffffu, (v[0].w & v[1].w & v[2].w & v[3].w & v[4].w & v[5].w) == 0x41800000u)) break; \
            RETRY_COUNT(); \
            KV_LOAD(hp); \
          } \
          PROF(25 + (hp)); \
          const uint32_t e = lane & 7, jt = ((lane >> 1) & 4) + (e >> 1); \
          const uint32_t row = ((((warp >> 1) ^ wg) & 1) << 5) + ((jt & 1) << 4) + ((warp & 1) << 3) + (jt & 6) + (e & 1); \
          const uint32_t kd = pV + wg * 8192 + row * 128, ksw = (row & 7) << 4; \
          _Pragma("unroll") for (int i = 0; i < 2; i++) \
            stsm_x4(kd + ((i * 32 + lhi) ^ ksw), pack_bf16(KVV(i * 8), KVV(i * 8 + 1)), pack_bf16(KVV(i * 8 + 2), KVV(i * 8 + 3)), \
                    pack_bf16(KVV(i * 8 + 4), KVV(i * 8 + 5)), pack_bf16(KVV(i * 8 + 6), KVV(i * 8 + 7))); \
          stsm_x4(kd + ((64u + lhi) ^ ksw), pack_bf16(KVV(16), 1.f), pack_bf16(KVV(17), 1.f), 0u, 0u); }
#pragma unroll 1
        for (int h = 0; h < 2; h++) {
          PROF(4 + h * 2);
          SITE(0);
          LANE_CONSTS();
          const uint32_t dsw = (uint32_t)(g ^ (2 * t)) << 4, dst = ((t & 2) ? pK : sbase + 12 * SLOT) + (r0 + g) * 128;
          float e[16], f[16];
          float mn0 = rmin16(st);
          asm volatile("" : "+f"(mn0)); SCHED_FENCE();
          float sa = exps16(e, st, -c0, mn0 * c0), mx0 = rmax16(st);
          asm volatile("" : "+f"(sa), "+f"(mx0)); PIN(e, 16); SITE(1);
          if (h) STG_WAIT();
          store16(e, sa, dst, dsw, 4);
          float sb = exps16(f, st, c0, -mx0 * c0), mn1 = rmin16(st + 2);
          asm volatile("" : "+f"(sb), "+f"(mn1)); PIN(f, 16); SITE(2);
          store16(f, sb, dst, dsw, 0);
          float sc = exps16(e, st + 2, -c1, mn1 * c1), mx1 = rmax16(st + 2);
          asm volatile("" : "+f"(sc), "+f"(mx1)); PIN(e, 16); SITE(3);
          store16(e, sc, dst + 1024, dsw, 4);
          float sd = exps16(f, st + 2, c1, -mx1 * c1);
          asm volatile("" : "+f"(sd)); PIN(f, 16); SITE(4);
          store16(f, sd, dst + 1024, dsw, 0);
          PROF(5 + h * 2);
          if (h) break;
          {
            float kv[20];
            ACC_DEF(kv, 20);
            fence_proxy_async_smem();
            STG_ARRIVE();
            KV_MMA(11);
            PUMP0();
            ACC_FENCE(kv, 20);
            KV_RED(0);
            STG_ARRIVE();
          }
#pragma unroll
          for (int i = 0; i < 32; i++) st[i] = st[32 + i];
        }
        float mq[8];
        uint4 v[6];
        {
          float kv[20];
          if (KT0) { LANE_CONSTS(); KV_LOAD(0); }
          mbar_wait(bar_stat2, par);
          LNSTEP(S1, 1);
          ub = bar_full + 240;
          PUMP1();
          if (wg == 0) bar_sync<BAR_SKEW, 256>();
          QSTEP(S1, RA_CUR, 1, {});
          if (wg == 1) bar_arrive<BAR_SKEW, 256>();
          QREL();
          if (KT0 == 2) { LANE_CONSTS(); KV_TILE(0); }
          mbar_wait(bar_done + 30 * 8, par);
          wgmma_wait<0>();
          ACC_FENCE(S1, 96);
          if (!(RLATE & 2)) REL(bar_done + 31 * 8);
          PROF(13);
          LANE_CONSTS();
          STAGE_V(S1 + 64, sbase + 3 * SLOT);
          fence_proxy_async_smem();
          STG_ARRIVE();
          if (RLATE & 2) REL(bar_done + 31 * 8);
#pragma unroll
          for (int i = 0; i < 32; i++) st[i] = S1[i];
          PIN(st, 32);
          PROF(16);
          ACC_DEF(kv, 20);
          KV_MMA(3);
          SCHED_FENCE();
          if (!KT0) KV_LOAD(0);
          extrema(mq, st, c0, c1);
          PIN(mq, 8);
          SCHED_FENCE();
          wgmma_wait<0>();
          ACC_FENCE(kv, 20);
          KV_RED(1);
          PROF(17);
        }
#pragma unroll 1
        for (int h = 0; h < 2; h++) {
          const uint32_t pO = sbase + (h ? 3 : 8) * SLOT;
          LANE_CONSTS();
          uint32_t fq[32];
          expp16(fq, st, -c0, mq[0], -c1, mq[1]); expp16(fq + 8, st, c0, mq[2], c1, mq[3]); PINU(fq, 16);
          PROF(18 + h * 14);
          SCHED_FENCE();
          if (h) {
            asm volatile("cp.async.bulk.wait_group.read 0;" ::: "memory");
            mbar_wait(bar_lx, par);
          }
          if (h || KT0 < 2) {
            KV_TILE(h);
            fence_proxy_async_smem();
            STG_ARRIVE();
          }
          SCHED_FENCE();
          expp16(fq + 16, st + 16, -c0, mq[4], -c1, mq[5]); PINU(fq + 16, 8);
          if (h || KT0 < 2) STG_WAIT();
          wgmma_wait<0>();
          ACC_FENCE(S1, 64);
          PROF(19 + h * 14);
          float o[4][20];
#define O_MMA(hh) { \
            const uint64_t db = make_desc(pV + (hh) * 8192, 16, 1024); \
            ACC_DEF(o[(hh) * 2], 20); ACC_DEF(o[(hh) * 2 + 1], 20); \
            wgmma_fence(); \
            wgmma_n40_rs<0>(o[(hh) * 2], fq + (hh) * 16, db + 256); wgmma_n40_rs<0>(o[(hh) * 2 + 1], fq + (hh) * 16 + 8, db); \
            wgmma_n40_rs<1>(o[(hh) * 2], fq + (hh) * 16 + 4, db + 384); wgmma_n40_rs<1>(o[(hh) * 2 + 1], fq + (hh) * 16 + 12, db + 128); \
            wgmma_commit(); }
          O_MMA(0);
          SCHED_FENCE();
          expp16(fq + 24, st + 16, c0, mq[6], c1, mq[7]); PINU(fq + 24, 8);
          SCHED_FENCE();
          PMASKS(true, O_BIT(l));
#pragma unroll
          for (int hh = 0; hh < 2; hh++) {
            if (hh && !OW) O_MMA(1);
            wgmma_wait<0>();
            ACC_FENCE(o[hh * 2], 20); ACC_FENCE(o[hh * 2 + 1], 20);
            if (!hh && OW) { O_MMA(1); SCHED_FENCE(); }
            const float* x = o[hh * 2];
            const float* y = o[hh * 2 + 1];
            const float rx0 = rcp_fast(x[17]), ry0 = rcp_fast(y[17]), rx1 = rcp_fast(x[19]), ry1 = rcp_fast(y[19]);
            const float i0 = rcp_fast(fmaf(x[16], rx0, y[16] * ry0) + 1e-6f), i1 = rcp_fast(fmaf(x[18], rx1, y[18] * ry1) + 1e-6f);
            const float ax0 = rx0 * i0, ay0 = ry0 * i0, ax1 = rx1 * i1, ay1 = ry1 * i1;
#pragma unroll
            for (int dp = 0; dp < 2; dp++)
              stsm_x4(pO + srowoff + ((hh * 64 + dp * 32 + lhi) ^ lsw),
                      PBIT0(pack_bf16(fmaf(x[dp * 8], ax0, y[dp * 8] * ay0), fmaf(x[dp * 8 + 1], ax0, y[dp * 8 + 1] * ay0))),
                      PBIT0(pack_bf16(fmaf(x[dp * 8 + 2], ax1, y[dp * 8 + 2] * ay1), fmaf(x[dp * 8 + 3], ax1, y[dp * 8 + 3] * ay1))),
                      PBIT1(pack_bf16(fmaf(x[dp * 8 + 4], ax0, y[dp * 8 + 4] * ay0), fmaf(x[dp * 8 + 5], ax0, y[dp * 8 + 5] * ay0))),
                      PBIT1(pack_bf16(fmaf(x[dp * 8 + 6], ax1, y[dp * 8 + 6] * ay1), fmaf(x[dp * 8 + 7], ax1, y[dp * 8 + 7] * ay1))));
          }
          PUBLISH_O();
          PROF(20 + h * 14);
          if (h) break;
#pragma unroll
          for (int i = 0; i < 32; i++) st[i] = S1[32 + i];
          PIN(st, 32);
          LOAD_X();
          bar_wg(wg);
          WSTEP();
          SCHED_FENCE();
          if (KVL == 0) KV_LOAD(1);
          extrema(mq, st, c0, c1);
          PIN(mq, 8);
          if (KVL == 1) { SCHED_FENCE(); KV_LOAD(1); }
          PROF(31);
        }
      }
      __syncwarp();
      if (elect_one()) mbar_arrive_local(bar_epi);
      bar_wg(wg);
#pragma unroll 1
      while (ub < bar_full + 384) {
        WSTEP();
        if (ub == bar_full + 8 * 41) { asm volatile("cp.async.bulk.wait_group.read 0;" ::: "memory"); PROF(35); }
        if (ub == bar_full + 8 * 42) PROF(36);
      }
      wgmma_wait<0>();
      ACC_FENCE(S1, 64);
      if (!RLATE) REL(bar_done + 47 * 8);
      PROF(37);
      {
        LANE_CONSTS();
        X_OUT(0, l < NLAYERS - 1);
        WARP_STORE(l < NLAYERS - 1 ? &tm_os : &tm_xo, pK, jj * 128, mm * 128 + (l < NLAYERS - 1 ? S_LEN : 0));
        if (RLATE) REL(bar_done + 47 * 8);
        if (l == NLAYERS - 1) {
          X_OUT(1, false);
          WARP_STORE(&tm_xo, pV, jj * 128 + 64, mm * 128);
          asm volatile("cp.async.bulk.wait_group 0;" ::: "memory");
        }
      }
#pragma unroll
      for (int i = 32; i < 64; i++) { uint32_t c; asm volatile("mov.b32 %0, %1;" : "=r"(c) : "f"(S1[i])); S1[i] = __uint_as_float(c); }
      PROF(38);
    }
    const int tid = threadIdx.x;
    if (tid == 0) {
      unsigned old = atomicAdd(&g_flags.done.v, 1);
      if (old == ep1 * NMAIN - 1) {
        asm volatile("st.relaxed.gpu.global.u32 [%0], %1;" :: "l"(&g_flags.epoch.v), "r"(ep1) : "memory");
      }
    }
    __syncwarp();
    cluster_sync();
  }
}

typedef CUresult (*PFN_encode)(CUtensorMap*, CUtensorMapDataType, cuuint32_t, void*, const cuuint64_t*, const cuuint64_t*,
                               const cuuint32_t*, const cuuint32_t*, CUtensorMapInterleave, CUtensorMapSwizzle,
                               CUtensorMapL2promotion, CUtensorMapFloatOOBfill);

CUtensorMap make_map(PFN_encode enc, const void* ptr, uint64_t inner, uint64_t outer, uint32_t box_inner, uint32_t box_outer,
                     CUtensorMapSwizzle swz = CU_TENSOR_MAP_SWIZZLE_128B) {
  CUtensorMap m;
  cuuint64_t dims[2] = {inner, outer};
  cuuint64_t strides[1] = {inner * 2};
  cuuint32_t box[2] = {box_inner, box_outer};
  cuuint32_t es[2] = {1, 1};
  enc(&m, CU_TENSOR_MAP_DATA_TYPE_BFLOAT16, 2, const_cast<void*>(ptr), dims, strides, box, es, CU_TENSOR_MAP_INTERLEAVE_NONE,
      swz, CU_TENSOR_MAP_L2_PROMOTION_L2_256B, CU_TENSOR_MAP_FLOAT_OOB_FILL_NONE);
  return m;
}

}

extern "C" void kernel_launch(void* const* d_in, const int* in_sizes, int n_in, void* d_out, int out_size) {
  (void)in_sizes; (void)n_in; (void)out_size;
  static PFN_encode enc = nullptr;
  if (!enc) {
    void* fn = nullptr;
    cudaDriverEntryPointQueryResult qr;
    cudaGetDriverEntryPoint("cuTensorMapEncodeTiled", &fn, cudaEnableDefault, &qr);
    enc = (PFN_encode)fn;
    cudaFuncSetAttribute(mega_kernel, cudaFuncAttributeMaxDynamicSharedMemorySize, SMEM_BYTES);
  }
  Params prm;
  prm.x0 = (const __nv_bfloat16*)d_in[0];
  prm.wA_qkv = (const __nv_bfloat16*)d_in[1];
  prm.wA_o = (const __nv_bfloat16*)d_in[2];
  prm.wB_qkv = (const __nv_bfloat16*)d_in[4];
  prm.wB_phi = (const __nv_bfloat16*)d_in[5];
  prm.wB_o = (const __nv_bfloat16*)d_in[6];
  prm.out = (__nv_bfloat16*)d_out;
  void *obuf = nullptr, *wf = nullptr;
  cudaGetSymbolAddress(&obuf, g_obuf);
  cudaGetSymbolAddress(&wf, g_wfold);
  CUtensorMap tm_x0 = make_map(enc, d_in[0], D_MODEL, S_LEN, 64, 128);
  CUtensorMap tm_xo = make_map(enc, d_out, D_MODEL, S_LEN, 64, 16);
  CUtensorMap tm_os = make_map(enc, obuf, D_MODEL, 2 * S_LEN, 64, 16);
  CUtensorMap tm_o = make_map(enc, obuf, D_MODEL, 2 * S_LEN, 64, 128);
  CUtensorMap tm_wf = make_map(enc, wf, 2048, D_MODEL, 64, 32);
  CUtensorMap tm_wqA = make_map(enc, d_in[1], 3 * D_MODEL, D_MODEL, 64, 32);
  CUtensorMap tm_wqB = make_map(enc, prm.wB_qkv, 3 * D_MODEL, D_MODEL, 64, 32);
  CUtensorMap tm_woA = make_map(enc, prm.wA_o, D_MODEL, D_MODEL, 64, 64);
  CUtensorMap tm_woB = make_map(enc, prm.wB_o, D_MODEL, D_MODEL, 64, 64);
  CUtensorMap tm_phi = make_map(enc, prm.wB_phi, 32, 1024, 32, 128, CU_TENSOR_MAP_SWIZZLE_64B);
  mega_kernel<<<NMAIN + NAUX, 384, SMEM_BYTES>>>(tm_x0, tm_xo, tm_os, tm_o, tm_wf, tm_wqA, tm_wqB, tm_woA, tm_woB, tm_phi, prm);
}
```

```cpp
#include <cuda_runtime.h>
#include <cuda.h>
#include <cuda_bf16.h>
#include <stdint.h>

#define NLAYERS 4

#define STAG1 0
#define HPUMP1 2
#define HPUMP2 1
#define ASKEW 2
#define FPUMP 3
#define PFGAP 100
#define POLLGAP 120
#define OW 1
#define AW0 1
#define RLATE 3
#define FSTART 0
#define MAPV 1
#define HW1 29
#define XPACE 0x06050401000000ull
#define XP0 4
#define HW0 18
#define XD 4
#define WFGAP 50
#define KT0 2
#define W23 0
#define AX 0
#define PF0 1
#define EARLY 2
#define BIGLIM 60.f
#define SUMLO 0x1p-100f
#define SUMHI 0x1p100f
#define KVL 1
#define BMASK 0x1F
#define ASITE 1
namespace {

constexpr int S_LEN = 2048, D_MODEL = 1024;
constexpr int NAUX = 4, NMAIN = 128;
constexpr int SLOT = 16384;
constexpr int QST = 24576;
constexpr int OFF_RA = 6 * SLOT, OFF_S = 10 * SLOT;
constexpr int OFF_HALO = 13 * SLOT, OFF_LNB = OFF_HALO  , OFF_ONES = OFF_HALO + 3072;
constexpr int OFF_ST = OFF_HALO + 7168  , OFF_PHI = OFF_HALO + 8192;
constexpr int OFF_BAR = 14 * SLOT;
constexpr int OFF_LNA = OFF_BAR + 1024;
constexpr int SMEM_BYTES = OFF_LNA + 2048;
#define WO_ASLOT(par) ((par) ? 0x9876CAB39876CA98ull : 0x98C76BA398C7698Cull)
constexpr unsigned long long WO_BSLOT = 0x5432105421054210ull;
__device__ __forceinline__ int srcb(int j, int i) { return (i + (i >= j)) & 7; }
__device__ __forceinline__ int kslice(int j, int i) { return i < 2 ? 2 * j + i : (i < 9 ? 2 * srcb(j, i - 2) : 2 * srcb(j, i - 9) + 1); }
__device__ __forceinline__ int wslice(int j, int s) { return 2 * ((s & 7) ? srcb(j, (s & 7) - 1) : j) + (s >> 3); }
constexpr int KVH = 6 * 128 * 4;

struct __align__(128) Flag { unsigned v; unsigned pad[31]; };
struct Flags {
  Flag xready[4][16];
  Flag wfready[8];
  Flag done;
  Flag epoch;
};

__device__ Flags g_flags;
__device__ __nv_bfloat16 g_obuf[2 * S_LEN * D_MODEL];
#define O_BIT(l) ((epoch * NLAYERS + (l) + 1) & 1u)
#define X_BIT(l) ((epoch * (NLAYERS - 1) + (l) + 1) & 1u)
__device__ __nv_bfloat16 g_wfold[D_MODEL * 2048];
__device__ uint4 g_halo[16 * 8 * 512];
__device__ __align__(128) float g_kv[2][32 * KVH];
__device__ __align__(128) uint2 g_colsum[2][1536][2];
__device__ __align__(128) uint2 g_stats[S_LEN * 8];
#define H_BIT(l) (NLAYERS > 2 ? (uint32_t)((l) == 0) : (ep1 & 1))
#define STAT_TAG(l) ((ep1 * NLAYERS + (l) + 1) & 3u)

#define RETRY_COUNT()
#define PRL 0
#define PRU 0
#define PROFL 1
#define PROFW 0
#define PROFT(i) do {} while (0)
#define PROF(i) do {} while (0)

__device__ __forceinline__ uint32_t smem_u32(const void* p) { return (uint32_t)__cvta_generic_to_shared(p); }
__device__ __forceinline__ bool elect_one() {
  uint32_t p;
  asm volatile("{\n.reg .pred p;\nelect.sync _|p, 0xffffffff;\nselp.u32 %0, 1, 0, p;\n}\n" : "=r"(p));
  return p != 0;
}
__device__ __forceinline__ void mbar_init(uint32_t bar, uint32_t cnt) {
  asm volatile("mbarrier.init.shared::cta.b64 [%0], %1;" :: "r"(bar), "r"(cnt));
}
__device__ __forceinline__ void mbar_expect_tx(uint32_t bar, uint32_t bytes) {
  asm volatile("mbarrier.arrive.expect_tx.shared::cta.b64 _, [%0], %1;" :: "r"(bar), "r"(bytes) : "memory");
}
#define mbar_wait(bar, parity) \
  asm volatile("{\n.reg .pred p, q;\nW_%=:\nmbarrier.try_wait.parity.shared::cta.b64 p, [%1], %2;\nadd.s32 %0, %0, -1;\n" \
               "setp.gt.and.s32 q, %0, 0, !p;\n@q bra.uni W_%=;\n}\n" : "+r"(budget) : "r"((uint32_t)(bar)), "r"((uint32_t)(parity)) : "memory")
#define mbar_wait_sl(bar, parity) \
  asm volatile("{\n.reg .pred p, q;\nW_%=:\nmbarrier.try_wait.parity.shared::cta.b64 p, [%1], %2, 20000;\nadd.s32 %0, %0, -64;\n" \
               "setp.gt.and.s32 q, %0, 0, !p;\n@q bra.uni W_%=;\n}\n" : "+r"(budget) : "r"((uint32_t)(bar)), "r"((uint32_t)(parity)) : "memory")
__device__ __forceinline__ void mbar_arrive_local(uint32_t bar) {
  asm volatile("mbarrier.arrive.shared::cta.b64 _, [%0];" :: "r"(bar) : "memory");
}
__device__ __forceinline__ void tma_load_2d(uint32_t dst, const CUtensorMap* tm, uint32_t bar, int c0, int c1) {
  asm volatile("cp.async.bulk.tensor.2d.shared::cluster.global.mbarrier::complete_tx::bytes [%0], [%1, {%3, %4}], [%2];"
               :: "r"(dst), "l"(tm), "r"(bar), "r"(c0), "r"(c1) : "memory");
}
__device__ __forceinline__ void tma_load_2d_mc(uint32_t dst, const CUtensorMap* tm, uint32_t bar, int c0, int c1) {
  asm volatile("cp.async.bulk.tensor.2d.shared::cluster.global.mbarrier::complete_tx::bytes.multicast::cluster [%0], [%1, {%3, %4}], [%2], %5;"
               :: "r"(dst), "l"(tm), "r"(bar), "r"(c0), "r"(c1), "h"((uint16_t)3) : "memory");
}
__device__ __forceinline__ void tma_store_2d(const CUtensorMap* tm, uint32_t src, int c0, int c1) {
  asm volatile("cp.async.bulk.tensor.2d.global.shared::cta.bulk_group [%0, {%2, %3}], [%1];"
               :: "l"(tm), "r"(src), "r"(c0), "r"(c1) : "memory");
}
__device__ __forceinline__ void bulk_commit_wait() {
  asm volatile("cp.async.bulk.commit_group;\ncp.async.bulk.wait_group 0;" ::: "memory");
}
__device__ __forceinline__ void prefetch_tmap(const CUtensorMap* tm) {
  asm volatile("prefetch.tensormap [%0];" :: "l"(tm) : "memory");
}
__device__ __forceinline__ void fence_proxy_async_global() { asm volatile("fence.proxy.async.global;" ::: "memory"); }
__device__ __forceinline__ void fence_proxy_async_smem() { asm volatile("fence.proxy.async.shared::cta;" ::: "memory"); }
__device__ __forceinline__ unsigned ld_relaxed(const unsigned* p) {
  unsigned v;
  asm volatile("ld.relaxed.gpu.global.u32 %0, [%1];" : "=r"(v) : "l"(p) : "memory");
  return v;
}
__device__ __forceinline__ void fence_acquire() { asm volatile("fence.acquire.gpu;" ::: "memory"); }
__device__ __forceinline__ void wait_flag(const unsigned* p, unsigned target) {
  int it = 0;
  while ((int)(ld_relaxed(p) - target) < 0 && ++it < (1 << 20)) {}
  fence_acquire();
}
__device__ __forceinline__ void signal_release(unsigned* p) {
  asm volatile("red.release.gpu.global.add.u32 [%0], 1;" :: "l"(p) : "memory");
}
template <int ID, int N> __device__ __forceinline__ void bar_arrive() { asm volatile("bar.arrive %0, %1;" :: "n"(ID), "n"(N) : "memory"); }
template <int ID, int N> __device__ __forceinline__ void bar_sync() { asm volatile("bar.sync %0, %1;" :: "n"(ID), "n"(N) : "memory"); }
__device__ __forceinline__ void bar_wg(int wg) { asm volatile("bar.sync %0, 128;" :: "r"(2 + wg) : "memory"); }
__device__ __forceinline__ void cluster_sync() {
  asm volatile("barrier.cluster.arrive.relaxed.aligned;\nbarrier.cluster.wait.aligned;" ::: "memory");
}
__device__ __forceinline__ void cluster_wait() { asm volatile("barrier.cluster.wait.acquire.aligned;" ::: "memory"); }
enum { BAR_X1 = 7, BAR_WF = 8  , BAR_SKEW = 10 };

__device__ __forceinline__ void wgmma_fence() { asm volatile("wgmma.fence.sync.aligned;" ::: "memory"); }
__device__ __forceinline__ void wgmma_commit() { asm volatile("wgmma.commit_group.sync.aligned;" ::: "memory"); }
template <int N> __device__ __forceinline__ void wgmma_wait() { asm volatile("wgmma.wait_group.sync.aligned %0;" :: "n"(N) : "memory"); }

template <int scale_d, int tnsp_b = 1> __device__ __forceinline__ void wgmma_n192(float* d, uint64_t descA, uint64_t descB) {
  asm volatile("{\n.reg .pred p;\nsetp.ne.b32 p, %98, 0;\n"
               "wgmma.mma_async.sync.aligned.m64n192k16.f32.bf16.bf16 {%0,%1,%2,%3,%4,%5,%6,%7,%8,%9,%10,%11,%12,%13,%14,%15,%16,%17,%18,%19,%20,%21,%22,%23,%24,%25,%26,%27,%28,%29,%30,%31,%32,%33,%34,%35,%36,%37,%38,%39,%40,%41,%42,%43,%44,%45,%46,%47,%48,%49,%50,%51,%52,%53,%54,%55,%56,%57,%58,%59,%60,%61,%62,%63,%64,%65,%66,%67,%68,%69,%70,%71,%72,%73,%74,%75,%76,%77,%78,%79,%80,%81,%82,%83,%84,%85,%86,%87,%88,%89,%90,%91,%92,%93,%94,%95}, %96, %97, p, 1, 1, 0, %99;\n}\n"
               : "+f"(d[0]), "+f"(d[1]), "+f"(d[2]), "+f"(d[3]), "+f"(d[4]), "+f"(d[5]), "+f"(d[6]), "+f"(d[7]), "+f"(d[8]), "+f"(d[9]), "+f"(d[10]), "+f"(d[11]), "+f"(d[12]), "+f"(d[13]), "+f"(d[14]), "+f"(d[15]), "+f"(d[16]), "+f"(d[17]), "+f"(d[18]), "+f"(d[19]), "+f"(d[20]), "+f"(d[21]), "+f"(d[22]), "+f"(d[23]), "+f"(d[24]), "+f"(d[25]), "+f"(d[26]), "+f"(d[27]), "+f"(d[28]), "+f"(d[29]), "+f"(d[30]), "+f"(d[31]), "+f"(d[32]), "+f"(d[33]), "+f"(d[34]), "+f"(d[35]), "+f"(d[36]), "+f"(d[37]), "+f"(d[38]), "+f"(d[39]), "+f"(d[40]), "+f"(d[41]), "+f"(d[42]), "+f"(d[43]), "+f"(d[44]), "+f"(d[45]), "+f"(d[46]), "+f"(d[47]), "+f"(d[48]), "+f"(d[49]), "+f"(d[50]), "+f"(d[51]), "+f"(d[52]), "+f"(d[53]), "+f"(d[54]), "+f"(d[55]), "+f"(d[56]), "+f"(d[57]), "+f"(d[58]), "+f"(d[59]), "+f"(d[60]), "+f"(d[61]), "+f"(d[62]), "+f"(d[63]), "+f"(d[64]), "+f"(d[65]), "+f"(d[66]), "+f"(d[67]), "+f"(d[68]), "+f"(d[69]), "+f"(d[70]), "+f"(d[71]), "+f"(d[72]), "+f"(d[73]), "+f"(d[74]), "+f"(d[75]), "+f"(d[76]), "+f"(d[77]), "+f"(d[78]), "+f"(d[79]), "+f"(d[80]), "+f"(d[81]), "+f"(d[82]), "+f"(d[83]), "+f"(d[84]), "+f"(d[85]), "+f"(d[86]), "+f"(d[87]), "+f"(d[88]), "+f"(d[89]), "+f"(d[90]), "+f"(d[91]), "+f"(d[92]), "+f"(d[93]), "+f"(d[94]), "+f"(d[95])
               : "l"(descA), "l"(descB), "n"(scale_d), "n"(tnsp_b));
}
template <int scale_d> __device__ __forceinline__ void wgmma4_n192(float* d, uint32_t da, uint32_t db) {
#define R_ "{%0,%1,%2,%3,%4,%5,%6,%7,%8,%9,%10,%11,%12,%13,%14,%15,%16,%17,%18,%19,%20,%21,%22,%23,%24,%25,%26,%27,%28,%29,%30,%31,%32,%33,%34,%35,%36,%37,%38,%39,%40,%41,%42,%43,%44,%45,%46,%47,%48,%49,%50,%51,%52,%53,%54,%55,%56,%57,%58,%59,%60,%61,%62,%63,%64,%65,%66,%67,%68,%69,%70,%71,%72,%73,%74,%75,%76,%77,%78,%79,%80,%81,%82,%83,%84,%85,%86,%87,%88,%89,%90,%91,%92,%93,%94,%95}"
  asm volatile("{\n.reg .pred p, q;\n.reg .b64 a, b;\nsetp.ne.b32 p, %98, 0;\nsetp.eq.b32 q, 0, 0;\nmov.b64 a, {%96, 0x40000040};\nmov.b64 b, {%97, 0x40000040};\n"
               "wgmma.mma_async.sync.aligned.m64n192k16.f32.bf16.bf16 " R_ ", a, b, p, 1, 1, 0, 1;\nadd.s64 a, a, 2;\nadd.s64 b, b, 128;\n"
               "wgmma.mma_async.sync.aligned.m64n192k16.f32.bf16.bf16 " R_ ", a, b, q, 1, 1, 0, 1;\nadd.s64 a, a, 2;\nadd.s64 b, b, 128;\n"
               "wgmma.mma_async.sync.aligned.m64n192k16.f32.bf16.bf16 " R_ ", a, b, q, 1, 1, 0, 1;\nadd.s64 a, a, 2;\nadd.s64 b, b, 128;\n"
               "wgmma.mma_async.sync.aligned.m64n192k16.f32.bf16.bf16 " R_ ", a, b, q, 1, 1, 0, 1;\n}\n"
               : "+f"(d[0]), "+f"(d[1]), "+f"(d[2]), "+f"(d[3]), "+f"(d[4]), "+f"(d[5]), "+f"(d[6]), "+f"(d[7]), "+f"(d[8]), "+f"(d[9]), "+f"(d[10]), "+f"(d[11]), "+f"(d[12]), "+f"(d[13]), "+f"(d[14]), "+f"(d[15]), "+f"(d[16]), "+f"(d[17]), "+f"(d[18]), "+f"(d[19]), "+f"(d[20]), "+f"(d[21]), "+f"(d[22]), "+f"(d[23]), "+f"(d[24]), "+f"(d[25]), "+f"(d[26]), "+f"(d[27]), "+f"(d[28]), "+f"(d[29]), "+f"(d[30]), "+f"(d[31]), "+f"(d[32]), "+f"(d[33]), "+f"(d[34]), "+f"(d[35]), "+f"(d[36]), "+f"(d[37]), "+f"(d[38]), "+f"(d[39]), "+f"(d[40]), "+f"(d[41]), "+f"(d[42]), "+f"(d[43]), "+f"(d[44]), "+f"(d[45]), "+f"(d[46]), "+f"(d[47]), "+f"(d[48]), "+f"(d[49]), "+f"(d[50]), "+f"(d[51]), "+f"(d[52]), "+f"(d[53]), "+f"(d[54]), "+f"(d[55]), "+f"(d[56]), "+f"(d[57]), "+f"(d[58]), "+f"(d[59]), "+f"(d[60]), "+f"(d[61]), "+f"(d[62]), "+f"(d[63]), "+f"(d[64]), "+f"(d[65]), "+f"(d[66]), "+f"(d[67]), "+f"(d[68]), "+f"(d[69]), "+f"(d[70]), "+f"(d[71]), "+f"(d[72]), "+f"(d[73]), "+f"(d[74]), "+f"(d[75]), "+f"(d[76]), "+f"(d[77]), "+f"(d[78]), "+f"(d[79]), "+f"(d[80]), "+f"(d[81]), "+f"(d[82]), "+f"(d[83]), "+f"(d[84]), "+f"(d[85]), "+f"(d[86]), "+f"(d[87]), "+f"(d[88]), "+f"(d[89]), "+f"(d[90]), "+f"(d[91]), "+f"(d[92]), "+f"(d[93]), "+f"(d[94]), "+f"(d[95])
               : "r"(da), "r"(db), "n"(scale_d));
#undef R_
}
template <int scale_d> __device__ __forceinline__ void wgmma4_n128(float* d, uint32_t da, uint32_t db) {
#define R_ "{%0,%1,%2,%3,%4,%5,%6,%7,%8,%9,%10,%11,%12,%13,%14,%15,%16,%17,%18,%19,%20,%21,%22,%23,%24,%25,%26,%27,%28,%29,%30,%31,%32,%33,%34,%35,%36,%37,%38,%39,%40,%41,%42,%43,%44,%45,%46,%47,%48,%49,%50,%51,%52,%53,%54,%55,%56,%57,%58,%59,%60,%61,%62,%63}"
  asm volatile("{\n.reg .pred p, q;\n.reg .b64 a, b;\nsetp.ne.b32 p, %66, 0;\nsetp.eq.b32 q, 0, 0;\nmov.b64 a, {%64, 0x40000040};\nmov.b64 b, {%65, 0x40000040};\n"
               "wgmma.mma_async.sync.aligned.m64n128k16.f32.bf16.bf16 " R_ ", a, b, p, 1, 1, 0, 1;\nadd.s64 a, a, 2;\nadd.s64 b, b, 128;\n"
               "wgmma.mma_async.sync.aligned.m64n128k16.f32.bf16.bf16 " R_ ", a, b, q, 1, 1, 0, 1;\nadd.s64 a, a, 2;\nadd.s64 b, b, 128;\n"
               "wgmma.mma_async.sync.aligned.m64n128k16.f32.bf16.bf16 " R_ ", a, b, q, 1, 1, 0, 1;\nadd.s64 a, a, 2;\nadd.s64 b, b, 128;\n"
               "wgmma.mma_async.sync.aligned.m64n128k16.f32.bf16.bf16 " R_ ", a, b, q, 1, 1, 0, 1;\n}\n"
               : "+f"(d[0]), "+f"(d[1]), "+f"(d[2]), "+f"(d[3]), "+f"(d[4]), "+f"(d[5]), "+f"(d[6]), "+f"(d[7]), "+f"(d[8]), "+f"(d[9]), "+f"(d[10]), "+f"(d[11]), "+f"(d[12]), "+f"(d[13]), "+f"(d[14]), "+f"(d[15]), "+f"(d[16]), "+f"(d[17]), "+f"(d[18]), "+f"(d[19]), "+f"(d[20]), "+f"(d[21]), "+f"(d[22]), "+f"(d[23]), "+f"(d[24]), "+f"(d[25]), "+f"(d[26]), "+f"(d[27]), "+f"(d[28]), "+f"(d[29]), "+f"(d[30]), "+f"(d[31]), "+f"(d[32]), "+f"(d[33]), "+f"(d[34]), "+f"(d[35]), "+f"(d[36]), "+f"(d[37]), "+f"(d[38]), "+f"(d[39]), "+f"(d[40]), "+f"(d[41]), "+f"(d[42]), "+f"(d[43]), "+f"(d[44]), "+f"(d[45]), "+f"(d[46]), "+f"(d[47]), "+f"(d[48]), "+f"(d[49]), "+f"(d[50]), "+f"(d[51]), "+f"(d[52]), "+f"(d[53]), "+f"(d[54]), "+f"(d[55]), "+f"(d[56]), "+f"(d[57]), "+f"(d[58]), "+f"(d[59]), "+f"(d[60]), "+f"(d[61]), "+f"(d[62]), "+f"(d[63])
               : "r"(da), "r"(db), "n"(scale_d));
#undef R_
}
template <int scale_d> __device__ __forceinline__ void wgmma_n32(float* d, uint64_t descA, uint64_t descB) {
  asm volatile("{\n.reg .pred p;\nsetp.ne.b32 p, %18, 0;\n"
               "wgmma.mma_async.sync.aligned.m64n32k16.f32.bf16.bf16 {%0,%1,%2,%3,%4,%5,%6,%7,%8,%9,%10,%11,%12,%13,%14,%15}, %16, %17, p, 1, 1, 0, 1;\n}\n"
               : "+f"(d[0]), "+f"(d[1]), "+f"(d[2]), "+f"(d[3]), "+f"(d[4]), "+f"(d[5]), "+f"(d[6]), "+f"(d[7]), "+f"(d[8]), "+f"(d[9]), "+f"(d[10]), "+f"(d[11]), "+f"(d[12]), "+f"(d[13]), "+f"(d[14]), "+f"(d[15])
               : "l"(descA), "l"(descB), "n"(scale_d));
}
template <int scale_d, int tnsp_a> __device__ __forceinline__ void wgmma_n40(float* d, uint64_t descA, uint64_t descB) {
  asm volatile("{\n.reg .pred p;\nsetp.ne.b32 p, %22, 0;\n"
               "wgmma.mma_async.sync.aligned.m64n40k16.f32.bf16.bf16 {%0,%1,%2,%3,%4,%5,%6,%7,%8,%9,%10,%11,%12,%13,%14,%15,%16,%17,%18,%19}, %20, %21, p, 1, 1, %23, 1;\n}\n"
               : "+f"(d[0]), "+f"(d[1]), "+f"(d[2]), "+f"(d[3]), "+f"(d[4]), "+f"(d[5]), "+f"(d[6]), "+f"(d[7]), "+f"(d[8]), "+f"(d[9]), "+f"(d[10]), "+f"(d[11]), "+f"(d[12]), "+f"(d[13]), "+f"(d[14]), "+f"(d[15]), "+f"(d[16]), "+f"(d[17]), "+f"(d[18]), "+f"(d[19])
               : "l"(descA), "l"(descB), "n"(scale_d), "n"(tnsp_a));
}
template <int scale_d> __device__ __forceinline__ void wgmma_n40_rs(float* d, const uint32_t* a, uint64_t descB) {
  asm volatile("{\n.reg .pred p;\nsetp.ne.b32 p, %25, 0;\n"
               "wgmma.mma_async.sync.aligned.m64n40k16.f32.bf16.bf16 {%0,%1,%2,%3,%4,%5,%6,%7,%8,%9,%10,%11,%12,%13,%14,%15,%16,%17,%18,%19}, {%20,%21,%22,%23}, %24, p, 1, 1, 1;\n}\n"
               : "+f"(d[0]), "+f"(d[1]), "+f"(d[2]), "+f"(d[3]), "+f"(d[4]), "+f"(d[5]), "+f"(d[6]), "+f"(d[7]), "+f"(d[8]), "+f"(d[9]), "+f"(d[10]), "+f"(d[11]), "+f"(d[12]), "+f"(d[13]), "+f"(d[14]), "+f"(d[15]), "+f"(d[16]), "+f"(d[17]), "+f"(d[18]), "+f"(d[19])
               : "r"(a[0]), "r"(a[1]), "r"(a[2]), "r"(a[3]), "l"(descB), "n"(scale_d));
}
__device__ __forceinline__ uint64_t make_desc(uint32_t addr, uint32_t lbo_bytes, uint32_t sbo_bytes) {
  return (uint64_t)((addr & 0x3FFFF) >> 4) | ((uint64_t)(lbo_bytes >> 4) << 16) | ((uint64_t)(sbo_bytes >> 4) << 32) | (1ull << 62);
}

__device__ __forceinline__ void ldsm_x4(uint32_t addr, uint32_t& r0, uint32_t& r1, uint32_t& r2, uint32_t& r3) {
  asm volatile("ldmatrix.sync.aligned.m8n8.x4.shared.b16 {%0,%1,%2,%3}, [%4];" : "=r"(r0), "=r"(r1), "=r"(r2), "=r"(r3) : "r"(addr) : "memory");
}
__device__ __forceinline__ void ldsm_x4_t(uint32_t addr, uint32_t& r0, uint32_t& r1, uint32_t& r2, uint32_t& r3) {
  asm volatile("ldmatrix.sync.aligned.m8n8.x4.trans.shared.b16 {%0,%1,%2,%3}, [%4];" : "=r"(r0), "=r"(r1), "=r"(r2), "=r"(r3) : "r"(addr) : "memory");
}
__device__ __forceinline__ void stsm_x4(uint32_t addr, uint32_t r0, uint32_t r1, uint32_t r2, uint32_t r3) {
  asm volatile("stmatrix.sync.aligned.m8n8.x4.shared.b16 [%0], {%1,%2,%3,%4};" :: "r"(addr), "r"(r0), "r"(r1), "r"(r2), "r"(r3) : "memory");
}
__device__ __forceinline__ void sts128(uint32_t addr, uint32_t a, uint32_t b, uint32_t c, uint32_t d) {
  asm volatile("st.shared.v4.u32 [%0], {%1,%2,%3,%4};" :: "r"(addr), "r"(a), "r"(b), "r"(c), "r"(d) : "memory");
}
__device__ __forceinline__ float lds32f(uint32_t addr) {
  float v;
  asm volatile("ld.shared.f32 %0, [%1];" : "=f"(v) : "r"(addr) : "memory");
  return v;
}
__device__ __forceinline__ void sts32f(uint32_t addr, float a) {
  asm volatile("st.shared.f32 [%0], %1;" :: "r"(addr), "f"(a) : "memory");
}
__device__ __forceinline__ void mma_bf16(float (&c)[4], uint32_t a0, uint32_t a1, uint32_t a2, uint32_t a3, uint32_t b0, uint32_t b1) {
  asm volatile("mma.sync.aligned.m16n8k16.row.col.f32.bf16.bf16.f32 {%0,%1,%2,%3}, {%4,%5,%6,%7}, {%8,%9}, {%0,%1,%2,%3};"
               : "+f"(c[0]), "+f"(c[1]), "+f"(c[2]), "+f"(c[3]) : "r"(a0), "r"(a1), "r"(a2), "r"(a3), "r"(b0), "r"(b1));
}
__device__ __forceinline__ void mma_bf16_z(float (&c)[4], uint32_t a0, uint32_t a1, uint32_t a2, uint32_t a3, uint32_t b0, uint32_t b1) {
  asm volatile("mma.sync.aligned.m16n8k16.row.col.f32.bf16.bf16.f32 {%0,%1,%2,%3}, {%4,%5,%6,%7}, {%8,%9}, {%10,%10,%10,%10};"
               : "=f"(c[0]), "=f"(c[1]), "=f"(c[2]), "=f"(c[3]) : "r"(a0), "r"(a1), "r"(a2), "r"(a3), "r"(b0), "r"(b1), "f"(0.f));
}
__device__ __forceinline__ uint32_t movm_t(uint32_t v) {
  uint32_t r;
  asm volatile("movmatrix.sync.aligned.m8n8.trans.b16 %0, %1;" : "=r"(r) : "r"(v));
  return r;
}
__device__ __forceinline__ uint32_t pack_bf16(float lo, float hi) {
  uint32_t r;
  asm("cvt.rn.bf16x2.f32 %0, %1, %2;" : "=r"(r) : "f"(hi), "f"(lo));
  return r;
}
__device__ __forceinline__ float bf_lo(uint32_t v) { return __uint_as_float(v << 16); }
__device__ __forceinline__ float bf_hi(uint32_t v) { return __uint_as_float(v & 0xFFFF0000u); }
__device__ __forceinline__ void split3(float x, uint32_t& h, uint32_t& m, uint32_t& l) {
  h = pack_bf16(x, 0.f); x -= bf_lo(h);
  m = pack_bf16(x, 0.f); x -= bf_lo(m);
  l = pack_bf16(x, 0.f);
}
__device__ __forceinline__ float ex2(float x) { float r; asm("ex2.approx.ftz.f32 %0, %1;" : "=f"(r) : "f"(x)); return r; }
__device__ __forceinline__ float rcp_fast(float x) { float r; asm("rcp.approx.ftz.f32 %0, %1;" : "=f"(r) : "f"(x)); return r; }
__device__ __forceinline__ void red_v4(float* p, float a, float b, float c, float d) {
  asm volatile("red.global.add.v4.f32 [%0], {%1, %2, %3, %4};" :: "l"(p), "f"(a), "f"(b), "f"(c), "f"(d) : "memory");
}
__device__ __forceinline__ uint4 ld_ll(const uint4* p) {
  uint4 v;
  asm volatile("{\n.reg .b64 a, b;\nld.relaxed.gpu.global.v2.b64 {a, b}, [%4];\nmov.b64 {%0, %1}, a;\nmov.b64 {%2, %3}, b;\n}\n"
               : "=r"(v.x), "=r"(v.y), "=r"(v.z), "=r"(v.w) : "l"(p) : "memory");
  return v;
}
__device__ __forceinline__ void st_b64(uint2* p, uint32_t a, uint32_t b) {
  asm volatile("{\n.reg .b64 v;\nmov.b64 v, {%1, %2};\nst.relaxed.gpu.global.b64 [%0], v;\n}\n" :: "l"(p), "r"(a), "r"(b) : "memory");
}
__device__ __forceinline__ void st_b128(uint4* p, uint32_t a, uint32_t b, uint32_t c, uint32_t d) {
  asm volatile("{\n.reg .b128 v;\nmov.b128 v, {%1, %2, %3, %4};\nst.relaxed.gpu.global.b128 [%0], v;\n}\n" :: "l"(p), "r"(a), "r"(b), "r"(c), "r"(d) : "memory");
}
__device__ __forceinline__ uint4 ld_b128(const uint4* p) {
  uint4 v;
  asm volatile("{\n.reg .b128 v;\nld.relaxed.gpu.global.b128 v, [%4];\nmov.b128 {%0, %1, %2, %3}, v;\n}\n" : "=r"(v.x), "=r"(v.y), "=r"(v.z), "=r"(v.w) : "l"(p) : "memory");
  return v;
}

constexpr float LOG2E = 1.4426950408889634f;

struct Params {
  const __nv_bfloat16* x0;
  const __nv_bfloat16* wA_qkv;
  const __nv_bfloat16* wA_o;
  const __nv_bfloat16* wB_qkv;
  const __nv_bfloat16* wB_phi;
  const __nv_bfloat16* wB_o;
  __nv_bfloat16* out;
};

#define ACC_DEF(d, n) _Pragma("unroll") for (int i_ = 0; i_ < (n); i_++) asm volatile("" : "=f"(d[i_]))
#define ACC_FENCE(d, n) _Pragma("unroll") for (int i_ = 0; i_ < (n); i_++) asm volatile("" : "+f"(d[i_]) :: "memory")
#define PIN(a, n) _Pragma("unroll") for (int i_ = 0; i_ < (n); i_++) asm volatile("" : "+f"((a)[i_]))
#define PINU(a, n) _Pragma("unroll") for (int i_ = 0; i_ < (n); i_++) asm volatile("" : "+r"((a)[i_]))

#define STAGE_V(acc, p0) { \
    _Pragma("unroll") for (int j_ = 0; j_ < 4; j_++) { \
      const float* a_ = (acc) + j_ * 8; \
      stsm_x4((p0) + (j_ >> 1) * 8192 + (srowoff >> 1) + ((((uint32_t)(j_ & 1) << 5) + lhi) ^ lsw2), \
              pack_bf16(rs0 * a_[0], rs0 * a_[1]), pack_bf16(rs1 * a_[2], rs1 * a_[3]), pack_bf16(rs0 * a_[4], rs0 * a_[5]), pack_bf16(rs1 * a_[6], rs1 * a_[7])); } }
#define FRAG(dst, acc, TR, grp) { \
    _Pragma("unroll") for (int i_ = 0; i_ < 16; i_++) { \
      const float r_ = (i_ & 1) ? rs1 : rs0; \
      const uint32_t w_ = pack_bf16(r_ * (acc)[2 * i_], r_ * (acc)[2 * i_ + 1]); \
      if (TR) (dst)[i_] = movm_t(w_); else (dst)[(i_ & 12) + (i_ & 1) * 2 + ((i_ >> 1) & 1)] = w_; } \
    if (warp == 7 && mm < 15) { \
      _Pragma("unroll") for (int j_ = 0; j_ < 4; j_++) \
        st_b128(g_halo + (size_t)(mm * 8 + jj) * 512 + ((grp) * 4 + j_) * 32 + lane, ((dst)[j_ * 4] & ~1u) | H_BIT(l), (dst)[j_ * 4 + 1], (dst)[j_ * 4 + 2], (dst)[j_ * 4 + 3]); } \
    PINU(dst, 16); }
#define FRAG_PUT(src, slot) if (warp < 7) { _Pragma("unroll") for (int j_ = 0; j_ < 4; j_++) \
      sts128(sbase + (slot) * SLOT + 2048 + warp * 2048 + j_ * 512 + lane * 16, (src)[j_ * 4], (src)[j_ * 4 + 1], (src)[j_ * 4 + 2], (src)[j_ * 4 + 3]); }
#define FRAG_GET(dst, slot) { _Pragma("unroll") for (int j_ = 0; j_ < 4; j_++) \
      asm volatile("ld.shared.v4.u32 {%0, %1, %2, %3}, [%4];" : "=r"((dst)[j_ * 4]), "=r"((dst)[j_ * 4 + 1]), "=r"((dst)[j_ * 4 + 2]), "=r"((dst)[j_ * 4 + 3]) \
                   : "r"(sbase + (slot) * SLOT + warp * 2048 + j_ * 512 + lane * 16) : "memory"); }
#define RW(j) (((j) >> 1) * 4 + ((j) & 1))
template <int POS> __device__ __forceinline__ float exps16_(float* o, const float* p) {
  float s[4];
#pragma unroll
  for (int j = 0; j < 16; j++) { o[j] = ex2(POS ? p[RW(j)] : -p[RW(j)]); if (j < 4) s[j] = o[j]; else s[j & 3] += o[j]; }
  const float r = (s[0] + s[1]) + (s[2] + s[3]);
  return r + __shfl_xor_sync(0xffffffffu, r, 1);
}
template <int POS> __device__ __forceinline__ void exps16_fix(float* o, const float* p, float& sum) {
  if (__builtin_expect(__any_sync(0xffffffffu, !(sum > SUMLO && sum < SUMHI)), 0)) {
    float m = p[0], q[32];
#pragma unroll
    for (int j = 1; j < 16; j++) m = POS ? fmaxf(m, p[RW(j)]) : fminf(m, p[RW(j)]);
    const float x = __shfl_xor_sync(0xffffffffu, m, 1);
    m = POS ? fmaxf(m, x) : fminf(m, x);
#pragma unroll
    for (int j = 0; j < 16; j++) q[RW(j)] = p[RW(j)] - m;
    sum = exps16_<POS>(o, q);
  }
}
__device__ __forceinline__ void store16(const float* e, float sum, uint32_t dst, uint32_t dsw, int c0) {
  const float inv = rcp_fast(sum);
#pragma unroll
  for (int j = 0; j < 2; j++)
    sts128(dst + (((c0 + j) << 4) ^ dsw), pack_bf16(e[j * 8] * inv, e[j * 8 + 1] * inv), pack_bf16(e[j * 8 + 2] * inv, e[j * 8 + 3] * inv),
           pack_bf16(e[j * 8 + 4] * inv, e[j * 8 + 5] * inv), pack_bf16(e[j * 8 + 6] * inv, e[j * 8 + 7] * inv));
}
template <int POS> __device__ __forceinline__ void expp16(uint32_t* o, float* p, bool big) {
  if (__builtin_expect(big, 0)) {
#pragma unroll
    for (int r = 0; r < 4; r += 2) {
      float m = p[r];
#pragma unroll
      for (int j = 1; j < 8; j++) m = POS ? fmaxf(m, p[r + RW(j)]) : fminf(m, p[r + RW(j)]);
#pragma unroll
      for (int s = 1; s <= 2; s <<= 1) { const float x = __shfl_xor_sync(0xffffffffu, m, s); m = POS ? fmaxf(m, x) : fminf(m, x); }
#pragma unroll
      for (int j = 0; j < 8; j++) p[r + RW(j)] -= m;
    }
  }
#pragma unroll
  for (int j = 0; j < 8; j++) o[j] = pack_bf16(ex2(POS ? p[2 * j] : -p[2 * j]), ex2(POS ? p[2 * j + 1] : -p[2 * j + 1]));
}
__device__ __forceinline__ void scale32(float* o, const float* p, float c0, float c1) {
#pragma unroll
  for (int i = 0; i < 32; i++) asm volatile("mul.f32 %0, %1, %2;" : "=f"(o[i]) : "f"(p[i]), "f"((i & 2) ? c1 : c0));
}
__device__ __forceinline__ bool any_big(const float* p) {
  float m[4];
#pragma unroll
  for (int i = 0; i < 32; i++) m[i & 3] = i < 4 ? fabsf(p[i]) : fmaxf(m[i & 3], fabsf(p[i]));
  return __any_sync(0xffffffffu, !(fmaxf(fmaxf(m[0], m[1]), fmaxf(m[2], m[3])) < BIGLIM));
}
#define SCHED_FENCE() asm volatile("pmevent 0;" ::: "memory")

__global__ void __cluster_dims__(2, 1, 1) __launch_bounds__(384, 1)
mega_kernel(const __grid_constant__ CUtensorMap tm_x0, const __grid_constant__ CUtensorMap tm_xo, const __grid_constant__ CUtensorMap tm_os,
            const __grid_constant__ CUtensorMap tm_o, const __grid_constant__ CUtensorMap tm_wf,
            const __grid_constant__ CUtensorMap tm_wqA, const __grid_constant__ CUtensorMap tm_wqB,
            const __grid_constant__ CUtensorMap tm_woA, const __grid_constant__ CUtensorMap tm_woB,
            const __grid_constant__ CUtensorMap tm_phi, const Params prm) {
  extern __shared__ __align__(1024) uint8_t smem_raw[];
  const uint32_t sbase = smem_u32(smem_raw);
  const uint32_t bar_full = sbase + OFF_BAR;
  const uint32_t bar_done = bar_full + 384;
  const uint32_t bar_stat = bar_full + 768, bar_stat2 = bar_full + 776, bar_epi = bar_full + 784, bar_phi = bar_full + 936  , bar_halo = bar_full + 904  ;
  const uint32_t bar_xr = bar_full + 800, bar_lx = bar_full + 808, bar_stg = bar_full + 832;
  const uint32_t bar_chk = bar_full + 848;

  const int warp = __shfl_sync(0xffffffffu, threadIdx.x >> 5, 0), lane = threadIdx.x & 31;
  uint32_t rank;
  asm volatile("mov.u32 %0, %%cluster_ctarank;" : "=r"(rank));
  const int aux = (int)blockIdx.x - NMAIN, tp = (int)(blockIdx.x >> 1) - 4;
  const int gp = tp < 0 ? 0 : (tp < 32 ? tp & 7 : 1 + (tp - 32) % 7), me = tp < 0 ? tp + 8 : (tp < 32 ? tp >> 3 : 4 + (tp - 32) / 7);
  const int jj = me, cc = gp;
  const int cta = aux >= 0 ? -1 : (cc * 8 + jj) * 2 + (int)rank;
  const int mm = cc * 2 + (int)rank;

#define LOAD_EPOCH() const unsigned epoch = ld_relaxed(&g_flags.epoch.v), ep1 = epoch + 1; (void)epoch
  int budget = 1 << 22;

  if (cta >= 0) {
    if (warp >= 8 && warp < 8 + EARLY && elect_one()) {
      const int u = warp - 8;
      const uint32_t fb = bar_full + u * 8;
      mbar_init(fb, 1);
      asm volatile("fence.mbarrier_init.release.cluster;" ::: "memory");
      fence_proxy_async_smem();
      mbar_expect_tx(fb, u < 2 ? QST + SLOT : QST);
      if (u < 2) tma_load_2d(sbase + OFF_S + u * SLOT, &tm_x0, fb, jj * 128 + u * 64, mm * 128);
#pragma unroll
      for (int i = 0; i < 6; i++) tma_load_2d(sbase + u * QST + i * 4096, &tm_wqA, fb, jj * 128 + (u >> 1) * 64 + (i >> 1) * 1024, jj * 128 + (u & 1) * 64 + (i & 1) * 32);
      if (u == 0) PROFT(472);
    }
    __syncwarp();
    {
      const int tx = threadIdx.x;
      const __nv_bfloat16* pf = (tx < 128) ? prm.x0 + (size_t)(mm * 128 + tx) * D_MODEL + jj * 128
                                           : prm.wA_qkv + (size_t)(jj * 128 + (tx & 63)) * 3072 + ((tx - 128) >> 6) * 1024 + jj * 128 + rank * 64;
      if (tx < 320) { if (PF0) asm volatile("prefetch.global.L2 [%0];" :: "l"(pf)); }
      else if (tx == 320) prefetch_tmap(&tm_x0);
      else if (tx == 352) prefetch_tmap(&tm_wqA);
      else if (tx == 383) asm volatile("prefetch.global.L2 [%0];" :: "l"(&g_flags.epoch.v));
    }
    if (elect_one()) {
#pragma unroll
      for (int i = 0; i < 4; i++) {
        const int u = warp * 4 + i;
        if (u >= EARLY) mbar_init(bar_full + u * 8, ((u >= 4 && u < 11) || (u > 32 && u != 40)) ? 2 : 1); mbar_init(bar_done + u * 8, 16);
      }
      mbar_init(bar_stat + warp * 16, 0x111111181182ull >> (4 * warp) & 15);
      mbar_init(bar_stat + warp * 16 + 8, 0x111111121811ull >> (4 * warp) & 15);
      mbar_init(bar_chk + 112 + (warp & 7) * 8, 1);
      asm volatile("fence.mbarrier_init.release.cluster;" ::: "memory");
    }
    __syncthreads();
    asm volatile("barrier.cluster.arrive.relaxed.aligned;" ::: "memory");
  }

  if (cta < 0) {
    LOAD_EPOCH();
    const uint32_t buf = sbase + warp * SLOT, bar = sbase + OFF_BAR + warp * 16;
    const uint32_t lsw = (lane & 7) << 4, lhi = (lane >> 4) << 4, lrow = (lane & 15) * 128;
    const bool el = elect_one();
    if (el) {
      mbar_init(bar, 1); mbar_init(bar + 8, 1);
      asm volatile("fence.mbarrier_init.release.cluster;" ::: "memory");
    }
#pragma unroll 1
    for (int rd = 0; rd < (NLAYERS > 1 ? 5 : 2); rd++) {
      if (rd >= 2 && warp >= 8) break;
      const int tk = rd < 2 ? aux * 12 + warp : aux * 8 + warp;
      const int half = tk & 1;
      const int blk = rd < 2 ? (tk >> 1) * 2 + rd : (4 - rd) * 16 + (tk >> 1);
      const CUtensorMap* tm = rd < 2 ? &tm_wqA : (rd == 2 ? &tm_wqB : &tm_wf);
      const int j0 = (blk & 15) >> 1;
#define AUX_LOAD(n) { const uint32_t d_ = buf + ((n) & 1) * 8192, b_ = bar + ((n) & 1) * 8; const int r_ = kslice(j0, 2 * (n) + half) * 64; \
        mbar_expect_tx(b_, 8192); tma_load_2d(d_, tm, b_, blk * 64, r_); tma_load_2d(d_ + 4096, tm, b_, blk * 64, r_ + 32); }
      if (el) {
        if (rd == 3) { wait_flag(&g_flags.wfready[j0].v, ep1 * 16); fence_proxy_async_global(); }
        AUX_LOAD(0); AUX_LOAD(1);
      }
      __syncwarp();
      float cs[8][4];
#pragma unroll
      for (int i = 0; i < 8; i++) cs[i][0] = cs[i][1] = cs[i][2] = cs[i][3] = 0.f;
#pragma unroll 1
      for (int n = 0; n < 8; n++) {
        const uint32_t tb = buf + (n & 1) * 8192 + lrow;
        mbar_wait(bar + (n & 1) * 8, (n >> 1) & 1);
#pragma unroll
        for (int i = 0; i < 16; i++) {
          uint32_t b0, b1, b2, b3;
          ldsm_x4_t(tb + (i >> 2) * 2048 + (((i & 3) * 32 + lhi) ^ lsw), b0, b1, b2, b3);
          mma_bf16(cs[2 * (i & 3)], 0x3F803F80u, 0x3F803F80u, 0x3F803F80u, 0x3F803F80u, b0, b1);
          mma_bf16(cs[2 * (i & 3) + 1], 0x3F803F80u, 0x3F803F80u, 0x3F803F80u, 0x3F803F80u, b2, b3);
        }
        __syncwarp();
        if (el && n < 6) AUX_LOAD(n + 2);
        __syncwarp();
      }
      if (lane < 4) {
#pragma unroll
        for (int i = 0; i < 8; i++) st_b64(&g_colsum[rd >= 2][blk * 32 + i * 4 + lane][half], __float_as_uint(cs[i][0]), (__float_as_uint(cs[i][1]) & ~3u) | (ep1 & 3));
      }
      __syncwarp();
    }
  } else if (warp >= 8) {
    asm volatile("setmaxnreg.dec.sync.aligned.u32 40;");
    if (warp == 8) {
      const bool el = elect_one();
      cluster_wait();
      if (el) {
#pragma unroll 1
        for (int l = 0; l < NLAYERS; l++) {
          const uint32_t par = l & 1;
          const CUtensorMap* tqk = par ? &tm_wf : &tm_wqA;
          const CUtensorMap* tv = par ? &tm_wqB : &tm_wqA;
          const CUtensorMap* two = par ? &tm_woB : &tm_woA;
          if (l == 1) { LOAD_EPOCH(); wait_flag(&g_flags.wfready[jj].v, ep1 * 16); fence_proxy_async_global(); }
#pragma unroll 1
          for (int u = l ? 0 : EARLY; u < 32; u++) {
            if (u >= 4) mbar_wait_sl(bar_done + (u - 4) * 8, par);
            else if (l) mbar_wait_sl(bar_done + (43 + u + (u >> 1)) * 8, par ^ 1);
            else if (u == 1) __nanosleep(STAG1);
            else if (u == 2 && !W23) mbar_wait_sl(bar_full, 0);
            const uint32_t fb = bar_full + u * 8;
            const bool res = u < 4 ? (l || u >= 2) : (u < 11 || (u >= 18 && u < 22));
            mbar_expect_tx(fb, res ? QST : QST + SLOT);
            const int row = kslice(jj, u < 4 ? u & 1 : (u < 18 ? u - 2 : (u < 22 ? u - 6 : u - 20))) * 64 + (int)rank * 32;
            const int ps = u < 4 ? u >> 1 : (u >= 18), col = jj * 128 + ps * 64;
            const int c0 = par ? jj * 128 + (ps ? 0 : 1024) : col;
            const uint32_t dst = sbase + (u & 3) * QST + rank * 4096;
            tma_load_2d_mc(dst, tqk, fb, c0, row);
            tma_load_2d_mc(dst + 8192, tqk, fb, c0 + (par ? 64 : 1024), row);
            tma_load_2d_mc(dst + 16384, tv, fb, col + 2048, row);
            if (l == PRL && u >= PRU && u < PRU + 4) PROFT(473 + u - PRU);
          }
#pragma unroll 1
          for (int s = 0; s < 16; s++) {
            if (s < 5) { if (s != 2 && s != 4) mbar_wait_sl(bar_done + (28 + s) * 8, par); }
            else if (s != 14) mbar_wait_sl(bar_done + (27 + s - (s == 15)) * 8, par);
            const uint32_t fb = bar_full + (32 + s) * 8;
            mbar_expect_tx(fb, SLOT);
            tma_load_2d_mc(sbase + rank * 8192 + (uint32_t)((WO_BSLOT >> (4 * s)) & 15) * SLOT, two, fb, jj * 128 + (int)rank * 64, wslice(jj, s) * 64);
            const int ts = s + par;
            if (s >= 5 && ts < 8) {
              mbar_expect_tx(bar_chk - 8 + ts * 8, SLOT);
              tma_load_2d(sbase + (uint32_t)((WO_ASLOT(par) >> (4 * ts)) & 15) * SLOT, &tm_o, bar_chk - 8 + ts * 8, wslice(jj, ts) * 64, mm * 128);
            }
          }
        }
      }
      __syncwarp();
    } else if (warp == 9) {
      const bool el = elect_one();
      if (el) {
        if (!EARLY) { PROFT(472); tma_load_2d(sbase + OFF_S, &tm_x0, bar_full, jj * 128, mm * 128); }
        if (EARLY < 2) { __nanosleep(STAG1); tma_load_2d(sbase + OFF_S + SLOT, &tm_x0, bar_full + 8, jj * 128 + 64, mm * 128); }
      }
      __syncwarp();
      LOAD_EPOCH();
#pragma unroll 1
      for (int lp = 0; lp < 4 * NLAYERS; lp++) {
        const int l = lp >> 2, ph = lp & 3;
        if (ph == 3) continue;
        const uint32_t par = l & 1;
        const unsigned* pp = reinterpret_cast<const unsigned*>(g_obuf + (ph >> 1) * 64 + (size_t)(mm * 128 + (ph ? 0 : S_LEN) + (lane & 7) * 16 + (jj & 1) * 8) * D_MODEL +
                                                               (jj >> 1) * 16 + srcb(jj, lane >> 3) * 128);
        const CUtensorMap* tm = lp ? &tm_o : &tm_x0;
        const int row = mm * 128 + ((ph || !l) ? 0 : S_LEN);
        const uint32_t bit = ph ? O_BIT(l) : X_BIT(l - 1);
        const uint32_t slots = ph ? (uint32_t)(WO_ASLOT(par) >> (ph * 32 - 28)) : 0x8769876u;
        const unsigned long long fr = ph == 0 ? XPACE : ph == 1 ? (par ? 0x353535351Full : 0x35351F1Eull) : (par ? 0x27262524232232ull : 0x27262524233232ull);
        uint32_t no = (lp == 0 || (lp & 7) == 1) ? 0 : ~0u, v0 = 0, v1 = 0;
        if (lp || !AX) mbar_wait_sl(ph ? bar_done + ((uint32_t)fr & 63) * 8 : (l ? bar_done + 47 * 8 : bar_full), ph ? par : (l ? par ^ 1 : 0));
        if (el && ph) PROFT(324 + l * 16 + ph);
        __syncwarp();
        if (no) { v0 = ld_relaxed(pp); __nanosleep(POLLGAP); v1 = ld_relaxed(pp); }
#pragma unroll 1
        for (int i = 0; i < (ph == 1 ? 4 + par : 7); i++, no >>= 8) {
#pragma unroll 1
          for (int it = 0; (no & 0xFF) && it < (1 << 18); it++) {
            no &= __ballot_sync(0xffffffffu, (v0 ^ bit) & 1) >> (8 * i);
            if (no) v0 = ld_relaxed(pp);
            if (!(no & 0xFF)) break;
            no &= __ballot_sync(0xffffffffu, (v1 ^ bit) & 1) >> (8 * i);
            if (no) v1 = ld_relaxed(pp);
          }
          if (ph || i >= XP0) mbar_wait_sl(bar_done + ((uint32_t)(fr >> (8 * i)) & 63) * 8, par);
          if (el) {
            if (i == 0) PROFT(320 + l * 16 + ph);
            const uint32_t cb = bar_chk + (ph >> 1) * 112 + i * 8;
            mbar_expect_tx(cb, SLOT);
            tma_load_2d(sbase + ((slots >> (4 * i)) & 15) * SLOT, tm, cb, srcb(jj, i) * 128 + (ph >> 1) * 64, row);
          }
          __syncwarp();
        }
        if (ph == 0 && el) {
          if (l) { wait_flag(&g_flags.xready[l][mm].v, ep1 * 8); fence_proxy_async_global(); }
#pragma unroll 1
          for (int u = 11; u < 34; u++) {
            if (u == 18) u = 22;
            mbar_wait_sl(bar_done + (u - 4) * 8, par);
            if (u == 32) mbar_expect_tx(bar_xr, 2 * SLOT);
            tma_load_2d(sbase + OFF_RA + (u & 3) * SLOT, tm, u < 32 ? bar_full + u * 8 : bar_xr, kslice(jj, u < 18 ? u - 2 : (u < 32 ? u - 20 : u - 32)) * 64, row);
          }
        }
        __syncwarp();
      }
      cluster_wait();
    } else {
      const int hw = warp - 10;
      LOAD_EPOCH();
      const bool el = elect_one();
      cluster_wait();
      if (hw == 0) {
        mbar_wait_sl(bar_full + 8, 0);
        if (lane < 7) prefetch_tmap(lane == 0 ? &tm_os : lane == 1 ? &tm_o : lane == 2 ? &tm_wf : lane == 3 ? &tm_wqB : lane == 4 ? &tm_woA : lane == 5 ? &tm_woB : &tm_phi);
#pragma unroll 1
        for (int i = 0; i < (NLAYERS > 1 ? 9 : 0); i++) {
          if (i == 0 || i == 5) mbar_wait_sl(bar_done + (i >> 1) * 12, 0);
          if (el) {
            if (i == 0) { mbar_expect_tx(bar_phi, 2 * SLOT + 8192); tma_load_2d(sbase + OFF_PHI, &tm_phi, bar_phi, 0, jj * 128); }
            else tma_load_2d(sbase + (i > 4 ? 10 : 12) * SLOT - 4096 + i * 4096, &tm_wqB, bar_phi, (i > 4 ? 896 : 0) + jj * 128 + ((i - 1) >> 1) * 64, mm * 64 + (~i & 1) * 32);
          }
          __syncwarp();
          __nanosleep(PFGAP);
        }
      } else {
#pragma unroll 1
        for (int b = 0; b < 2; b++) {
          float4* z = reinterpret_cast<float4*>(g_kv[b] + (jj * 4) * KVH + mm * (4 * KVH / 16)) + lane;
#pragma unroll
          for (int i = 0; i < 6; i++) z[i * 32] = make_float4(0.f, 0.f, 0.f, 0.f);
        }
#pragma unroll 1
        for (int i = 0; i < 16; i++) {
          const int b = i >> 2;
          const uint32_t v = (b == 0 ? O_BIT(0) : b == 1 ? X_BIT(0) : H_BIT(0)) + 1;
          uint4* p = b < 2 ? reinterpret_cast<uint4*>(g_obuf + (size_t)(b * S_LEN + mm * 128 + (i & 3) * 32 + (lane >> 3) * 8) * D_MODEL + jj * 128 + (b ? 0 : 64)) + (lane & 7)
                           : g_halo + (size_t)(mm * 8 + jj) * 512 + i * 32 + lane;
          *p = make_uint4(v, v, v, v);
        }
        fence_proxy_async_global();
      }
      __syncwarp();
      uint32_t chkp = 0;
#pragma unroll 1
      for (int lp = 0; lp < 4 * NLAYERS; lp++) {
        const int l = lp >> 2, ph = (lp & 3) == 2 ? 2 - hw : (lp & 3);
        const uint32_t par = l & 1;
        int lane; asm volatile("mov.u32 %0, %%laneid;" : "=r"(lane));
        if ((lp & 3) == 2 || (hw && ph == 0)) {
          const uint32_t bit = ph ? O_BIT(l) : X_BIT(l - 1);
          uint32_t slots = ph ? (uint32_t)(WO_ASLOT(par) >> (ph * 32 - 28)) : 0x8769876u;
          const uint32_t a0 = sbase + (lane & 7) * 132 + (lane >> 3) * 32;
#pragma unroll 1
          for (int c = 0; c < 7; c++, slots >>= 4) {
            const uint32_t cb = bar_chk + 112 - hw * 112 + c * 8;
#pragma unroll 1
            for (int it = 0; it < (1 << 12); it++) {
              mbar_wait_sl(cb, (chkp >> c) & 1);
              chkp ^= 1u << c;
              if (el && c == 0) PROFT(ph == 1 ? 480 + l * 2 : 488 + l * 2 + (ph >> 1));
              if (lp == 0) break;
              uint32_t bad;
              asm volatile("{\n.reg .b32 w<16>;\n"
                           "ld.shared.u32 w0, [%1 + 0];\n"
                           "ld.shared.u32 w1, [%1 + 1024];\n"
                           "ld.shared.u32 w2, [%1 + 2048];\n"
                           "ld.shared.u32 w3, [%1 + 3072];\n"
                           "ld.shared.u32 w4, [%1 + 4096];\n"
                           "ld.shared.u32 w5, [%1 + 5120];\n"
                           "ld.shared.u32 w6, [%1 + 6144];\n"
                           "ld.shared.u32 w7, [%1 + 7168];\n"
                           "ld.shared.u32 w8, [%1 + 8192];\n"
                           "ld.shared.u32 w9, [%1 + 9216];\n"
                           "ld.shared.u32 w10, [%1 + 10240];\n"
                           "ld.shared.u32 w11, [%1 + 11264];\n"
                           "ld.shared.u32 w12, [%1 + 12288];\n"
                           "ld.shared.u32 w13, [%1 + 13312];\n"
                           "ld.shared.u32 w14, [%1 + 14336];\n"
                           "ld.shared.u32 w15, [%1 + 15360];\n"
                           "lop3.b32 w0, w0, w1, %2, 0x7E;\n"
                           "lop3.b32 w2, w2, w3, %2, 0x7E;\n"
                           "lop3.b32 w4, w4, w5, %2, 0x7E;\n"
                           "lop3.b32 w6, w6, w7, %2, 0x7E;\n"
                           "lop3.b32 w8, w8, w9, %2, 0x7E;\n"
                           "lop3.b32 w10, w10, w11, %2, 0x7E;\n"
                           "lop3.b32 w12, w12, w13, %2, 0x7E;\n"
                           "lop3.b32 w14, w14, w15, %2, 0x7E;\n"
                           "lop3.b32 w0, w0, w2, w4, 0xFE;\nlop3.b32 w6, w6, w8, w10, 0xFE;\nlop3.b32 w0, w0, w12, w14, 0xFE;\nlop3.b32 %0, w0, w6, 1, 0xA8;\n}\n"
                           : "=r"(bad) : "r"(a0 + (slots & 15) * SLOT), "r"(bit) : "memory");
              if (__all_sync(0xffffffffu, bad == 0)) break;
              if (el) {
                fence_proxy_async_smem();
                mbar_expect_tx(cb, SLOT);
                tma_load_2d(sbase + (slots & 15) * SLOT, &tm_o, cb, srcb(jj, c) * 128 + (ph >> 1) * 64, mm * 128 + (ph ? 0 : S_LEN));
                RETRY_COUNT();
              }
              __syncwarp();
            }
            if (el) { mbar_arrive_local(bar_full + (c + (ph ? 25 + ph * 8 : 4)) * 8); if (lp == PRL * 4 && c == 0) PROFT(477); }
            __syncwarp();
          }
          if (ph) continue;
#pragma unroll 1
          for (int hp = 0; hp < 2; hp++) {
            const uint4* src = reinterpret_cast<const uint4*>(g_colsum[par][jj * 64 + hp * 32 + lane]);
            uint32_t bad;
            int it = 0;
            float c[6];
            do {
              bad = 0;
#pragma unroll
              for (int p = 0; p < 3; p++) {
                const uint4 v = ld_ll(src + ((par && p < 2) ? (hp ? -32 : 512) + p * 32 : p * 512));
                bad |= (v.y ^ ep1) | (v.w ^ ep1);
                c[2 * p] = __uint_as_float(v.x) + __uint_as_float(v.z); c[2 * p + 1] = __uint_as_float(v.y) + __uint_as_float(v.w);
              }
              bad &= 3;
              if (bad) __nanosleep(300);
            } while (bad && ++it < (1 << 16));
#pragma unroll
            for (int p = 0; p < 6; p++) {
              uint32_t h, m, lo;
              split3(c[p], h, m, lo);
              sts128(sbase + OFF_LNB + hp * 4096 + (p >> 1) * 1024 + lane * 32 + (p & 1) * 16, h | (m << 16), h | (lo << 16), h | (m << 16), lo | (m << 16));
            }
            fence_proxy_async_smem();
            __syncwarp();
            if (el) { mbar_arrive_local(hp ? bar_stat2 : bar_stat); if (hp == 0) PROFT(324 + l * 16); }
            __syncwarp();
          }
          continue;
        } else if (ph == 0) {
          mbar_wait_sl(bar_done + 24, par);
          const uint4* sp = reinterpret_cast<const uint4*>(g_stats + (size_t)(mm * 128) * 8) + lane;
#pragma unroll 1
          for (int hf = 0; hf < 4; hf++) {
            uint4 v[4];
            uint32_t bad;
            int it = 0;
            do {
              bad = 0;
#pragma unroll
              for (int i = 0; i < 4; i++) { v[i] = ld_ll(sp + (hf * 4 + i) * 32); bad |= (v[i].y ^ STAT_TAG(l)) | (v[i].w ^ STAT_TAG(l)); }
              bad &= 3;
              if (bad) __nanosleep(200);
            } while (bad && ++it < (1 << 16));
            __syncwarp();
            float mean = 0.f, m2 = 0.f;
#pragma unroll
            for (int i = 0; i < 4; i++) {
              float a = __uint_as_float(v[i].x) + __uint_as_float(v[i].z);
              a += __shfl_xor_sync(0xffffffffu, a, 1); a += __shfl_xor_sync(0xffffffffu, a, 2);
              a *= 0.125f;
              const float e0 = __uint_as_float(v[i].x) - a, e1 = __uint_as_float(v[i].z) - a;
              float q = fmaf(fmaf(e0, e0, e1 * e1), 128.f, __uint_as_float(v[i].y) + __uint_as_float(v[i].w));
              q += __shfl_xor_sync(0xffffffffu, q, 1); q += __shfl_xor_sync(0xffffffffu, q, 2);
              if ((lane & 3) == i) { mean = a; m2 = q; }
            }
            const uint32_t row = hf * 32 + (lane & 3) * 8 + (lane >> 2);
            uint32_t h, m, lo;
            split3(-0.5f * mean, h, m, lo);
            sts128(sbase + OFF_LNA + row * 16, h | (h << 16), m | (h << 16), lo | (m << 16), m | (lo << 16));
            sts32f(sbase + OFF_ST + row * 4, rsqrtf(m2 * (1.f / 1024.f) + 1e-5f));
          }
          fence_proxy_async_smem();
          __syncwarp();
          if (el) { mbar_arrive_local(bar_stat); PROFT(323 + l * 16); }
          __syncwarp();
#pragma unroll 1
          for (int i = 0; i < 8 - 4 * l; i++) {
            asm volatile("prefetch.global.L2 [%0];" :: "l"(i < 4 ? (l ? prm.wB_o : prm.wA_o) + (size_t)cta * 8192 + i * 2048 + lane * 64
                                                                 : prm.wB_qkv + (size_t)(cta * 8 + (i - 4) * 2 + (lane >> 4)) * 3072 + 2048 + (lane & 15) * 64));
            __nanosleep(PFGAP);
          }
          continue;
        }
        if (ph == 1) {
          if (par) continue;
#pragma unroll 1
          for (int i = 0; i < 2; i++) {
            if (i && lp + hw == 1 && NLAYERS > 1) {
#pragma unroll 1
              for (int c = 0; c < 8; c++) {
                if (!(c & 3)) asm volatile("bar.sync %0, 288;" :: "r"(BAR_WF + (c >> 2)) : "memory");
                if (el) {
                  tma_store_2d(&tm_wf, sbase + 11 * SLOT + c * 4096, (c < 4 ? 1024 : -128) + jj * 128 + (c >> 1) * 64, mm * 64 + (c & 1) * 32);
                  if ((c & 3) == 3) {
                    asm volatile("cp.async.bulk.commit_group;\ncp.async.bulk.wait_group.read 0;" ::: "memory");
                    mbar_arrive_local(bar_phi + (c >> 2) * 8);
                  } else __nanosleep(WFGAP);
                }
                __syncwarp();
              }
              if (el) { bulk_commit_wait(); signal_release(&g_flags.wfready[jj].v); PROFT(335); }
              __syncwarp();
            }
            mbar_wait_sl(bar_done + (i ? HW1 : (hw ? 19 : HW0)) * 8, 0);
            if (lp + hw == 2 && NLAYERS > 1) mbar_wait_sl(bar_phi, 1);
            const uint4* src = g_halo + (size_t)(mm * 8 + jj - 8) * 512 + i * 256 + hw * 128 + lane;
            uint4 v[4];
            int it = 0;
            bool ok;
            do {
#pragma unroll
              for (int j = 0; j < 4; j++) v[j] = mm ? ld_b128(src + j * 32) : make_uint4(H_BIT(l), 0, 0, 0);
              ok = __all_sync(0xffffffffu, (((v[0].x ^ H_BIT(l)) | (v[1].x ^ H_BIT(l)) | (v[2].x ^ H_BIT(l)) | (v[3].x ^ H_BIT(l))) & 1) == 0);
            } while (!ok && ++it < (1 << 16));
#pragma unroll
            for (int j = 0; j < 4; j++) sts128(sbase + OFF_S + hw * SLOT + j * 512 + lane * 16, v[j].x, v[j].y, v[j].z, v[j].w);
            __syncwarp();
            if (el) { mbar_arrive_local(bar_halo + hw * 8); PROFT(331 + l * 16 + i * 2 + hw); }
            __syncwarp();
          }
        } else if (hw == 0 && l < NLAYERS - 1) {
          bar_sync<BAR_X1, 288>();
          if (el) {
            PROFT(328 + l * 16);
            mbar_wait_sl(bar_full + XD * 8, par ^ 1);
            tma_store_2d(&tm_o, sbase + 11 * SLOT, jj * 128 + 64, mm * 128 + S_LEN);
            bulk_commit_wait();
            signal_release(&g_flags.xready[l + 1][mm].v);
            PROFT(330 + l * 16);
          }
          __syncwarp();
        }
      }
    }
    cluster_sync();
  } else {
    asm volatile("setmaxnreg.inc.sync.aligned.u32 232;");
    LOAD_EPOCH();
    const int wg = warp >> 2;
    const int r0 = warp * 16;
    const uint32_t pK = sbase + OFF_S, pV = sbase + OFF_S + SLOT;
#define PMASKS(on, bit) const uint32_t pm0 = ((on) && t == (g & 3) && (g >> 2) == (g & 1)), pm1 = ((on) && t == (g & 3) && (g >> 2) != (g & 1)), pbit = (bit)
#define PBIT0(w) (((w) & ~pm0) | (pbit & pm0))
#define PBIT1(w) (((w) & ~pm1) | (pbit & pm1))
#define LANE_CONSTS() \
    int lane; asm volatile("mov.u32 %0, %%laneid;" : "=r"(lane)); \
    const int g = lane >> 2, t = lane & 3; \
    const uint32_t srowoff = (r0 + (lane & 15)) * 128, lsw = (lane & 7) << 4, lhi = (lane >> 4) << 4, lsw2 = (lane & 6) << 3; \
    (void)g; (void)t; (void)srowoff; (void)lsw; (void)lhi; (void)lsw2;
    uint32_t stgp = 0, peer;
    asm volatile("mapa.shared::cluster.u32 %0, %1, %2;" : "=r"(peer) : "r"(sbase), "r"(rank ^ 1));
    peer -= sbase;
    const uint32_t dA0 = (((sbase & 0x3FFFF) + wg * 8192) >> 4) | 0x10000u, dB0 = ((sbase & 0x3FFFF) >> 4) | 0x2000000u;
    cluster_wait();
#define DESC(lo, hi) ((uint64_t)(uint32_t)(lo) | ((uint64_t)(hi) << 32))
#define STG_ARRIVE() { __syncwarp(); if (elect_one()) mbar_arrive_local(bar_stg); }
#define STG_WAIT() { mbar_wait(bar_stg, stgp); stgp ^= 1; }
#define PROFS() do {} while (0)
#define REL(addr) { if (elect_one()) { mbar_arrive_local(addr); asm volatile("mbarrier.arrive.shared::cluster.b64 _, [%0];" :: "r"((addr) + peer) : "memory"); } }
#define QSTEP(ACC, DA, SC, PRE) { \
      const uint32_t da = (DA), db = dB0 + (ub & 0x18) * (QST >> 7); \
      mbar_wait(ub, par); \
      PRE; \
      wgmma_fence(); \
      wgmma4_n192<SC>(ACC, da, db); \
      wgmma_commit(); PROFS(); }
#define QREL() { wgmma_wait<1>(); REL(ub + 376); ub += 8; }
#define RA_CUR (dA0 + (OFF_RA >> 4) + (ub & 0x18) * (SLOT >> 7))
#define PUMP1() { QSTEP(S1, RA_CUR, 1, {}); QREL(); }
#define PUMP0() { PUMP1(); SCHED_FENCE(); }
#define PUMP() if (h == 0) PUMP1()
#define WSTEP() { \
      const uint32_t s4 = (ub - bar_full - 256) >> 1; \
      const uint32_t da = dA0 + (((uint32_t)(WO_ASLOT(par) >> s4) & 15) << 10), db = dB0 + (((uint32_t)(WO_BSLOT >> s4) & 15) << 10); \
      mbar_wait(ub, par); \
      wgmma_fence(); \
      wgmma4_n128<1>(S1, da, db); \
      wgmma_commit(); PROFS(); \
      wgmma_wait<1>(); \
      if (s4) REL(ub + 376); \
      ub += 8; }
#define PUMPS(n) { _Pragma("unroll 1") for (int i_ = 0; i_ < (n); i_++) PUMP1(); }
#define SITE(n) { if ((BMASK >> (n)) & 1) PUMP1(); SCHED_FENCE(); }
#define LNSTEP(ACC, hh) { wgmma_fence(); wgmma_n192<1, 0>(ACC, make_desc(sbase + OFF_LNA + wg * 1024, 0, 128) ^ (1ull << 62), make_desc(sbase + OFF_LNB + (hh) * 4096, 0, 128) ^ (1ull << 62)); }
#define WARP_STORE(tm, tile, col, row) { fence_proxy_async_smem(); __syncwarp(); \
      if (elect_one()) { tma_store_2d(tm, (tile) + r0 * 128, col, (row) + r0); asm volatile("cp.async.bulk.commit_group;" ::: "memory"); } __syncwarp(); }
#define PUBLISH_O() WARP_STORE(&tm_os, pO, jj * 128 + h * 64, mm * 128)
#define X_OUT(pc, on) { \
      PMASKS(on, X_BIT(l)); \
      _Pragma("unroll") for (int j = (pc) * 4; j < (pc) * 4 + 4; j++) \
        stsm_x4(pK + (pc) * SLOT + srowoff + ((((uint32_t)(j & 3) << 5) + lhi) ^ lsw), \
                PBIT0(pack_bf16(S1[j * 8 + 0], S1[j * 8 + 1])), PBIT0(pack_bf16(S1[j * 8 + 2], S1[j * 8 + 3])), \
                PBIT1(pack_bf16(S1[j * 8 + 4], S1[j * 8 + 5])), PBIT1(pack_bf16(S1[j * 8 + 6], S1[j * 8 + 7]))); }
#define REST_P1(SKEW) { \
      mbar_wait(bar_stat2, par); \
      LNSTEP(S1, 1); \
      _Pragma("unroll 1") while (ub < bar_full + 256) { \
        if (ub == bar_full + 256 - 8 * (SKEW) && wg == 0) bar_sync<BAR_SKEW, 256>(); \
        QSTEP(S1, RA_CUR, 1, {}); \
        if (ub == bar_full + 248 && wg == 1) bar_arrive<BAR_SKEW, 256>(); \
        QREL(); \
      } \
      mbar_wait(bar_done + (31 - (SKEW)) * 8, par);        \
      wgmma_wait<0>(); \
      ACC_FENCE(S1, 96); \
      REL(bar_done + 31 * 8); \
      PROF(13); }
#define FOLD(tile, rd) { \
          LANE_CONSTS(); \
          float d[32]; \
          ACC_DEF(d, 32); \
          mbar_wait(bar_phi, 0); \
          wgmma_fence(); \
          _Pragma("unroll") for (int i = 0; i < 2; i++) { \
            const uint64_t da = make_desc((tile) + wg * 8192 + i * 64, 16, 1024); \
            const uint64_t db = make_desc(sbase + OFF_PHI + wg * 4096 + i * 2048, 16, 512) ^ (3ull << 62); \
            wgmma_n32<0>(d + i * 16, da, db); wgmma_n32<1>(d + i * 16, da + 2, db + 64); \
          } \
          wgmma_commit(); \
          PUMP0(); \
          ACC_FENCE(d, 32); \
          bar_wg(wg); \
          _Pragma("unroll") for (int i = 0; i < 4; i++) { \
            const float* x = d + (i & 1) * 8 + (i >> 1) * 2; \
            if (rd) sts128((tile) + wg * 8192 + ((warp & 3) * 16 + (i >> 1) * 8 + g) * 128 + (((2 * t + (i & 1)) ^ g) << 4), \
                           pack_bf16(x[0], x[1]), pack_bf16(x[4], x[5]), pack_bf16(x[16], x[17]), pack_bf16(x[20], x[21])); \
            else stsm_x4((tile) + srowoff + ((((uint32_t)i << 5) + lhi) ^ lsw), pack_bf16(d[i * 8], d[i * 8 + 1]), pack_bf16(d[i * 8 + 2], d[i * 8 + 3]), \
                         pack_bf16(d[i * 8 + 4], d[i * 8 + 5]), pack_bf16(d[i * 8 + 6], d[i * 8 + 7])); \
          } \
          }
#define LOAD_X0(base) \
      _Pragma("unroll") for (int j = 0; j < 8; j++) { \
        uint32_t x0, x1, x2, x3; \
        ldsm_x4((base) + (j >> 2) * SLOT + srowoff + ((((uint32_t)(j & 3) << 5) + lhi) ^ lsw), x0, x1, x2, x3); \
        S1[j * 8 + 0] = bf_lo(x0); S1[j * 8 + 1] = bf_hi(x0); S1[j * 8 + 2] = bf_lo(x1); S1[j * 8 + 3] = bf_hi(x1); \
        S1[j * 8 + 4] = bf_lo(x2); S1[j * 8 + 5] = bf_hi(x2); S1[j * 8 + 6] = bf_lo(x3); S1[j * 8 + 7] = bf_hi(x3); \
      }
#define LOAD_X() { \
      wgmma_wait<0>(); \
      mbar_wait(bar_xr, par); \
      LOAD_X0(sbase + OFF_RA); \
      ACC_FENCE(S1, 64); \
      __syncwarp(); if (elect_one()) mbar_arrive_local(bar_lx); }

    float S1[96];
#pragma unroll
    for (int i = 0; i < 64; i++) S1[i] = 0.f;
#pragma unroll 1
    for (int l = 0; l < NLAYERS; l++) {
      const uint32_t par = l & 1;
      bar_wg(wg);
      PROF(0);
      uint32_t ub = bar_full;
      float S0[96];
      {
        LANE_CONSTS();
        ACC_DEF(S0, 96);
        QSTEP(S0, dA0 + (OFF_S >> 4), 0, {});
        ub += 8;
        PROF(1);
        if (l == 0) { mbar_wait(ub, 0); LOAD_X0(pK); }
        else { X_OUT(1, false); fence_proxy_async_smem(); }
        SCHED_FENCE();
        {
          float a0 = S1[0], a1 = S1[2], b0 = S1[1], b1 = S1[3];
#pragma unroll
          for (int i = 4; i < 64; i += 4) { a0 += S1[i]; b0 += S1[i + 1]; a1 += S1[i + 2]; b1 += S1[i + 3]; }
          a0 += b0; a1 += b1;
          a0 += __shfl_xor_sync(0xffffffffu, a0, 1); a1 += __shfl_xor_sync(0xffffffffu, a1, 1);
          a0 += __shfl_xor_sync(0xffffffffu, a0, 2); a1 += __shfl_xor_sync(0xffffffffu, a1, 2);
          a0 *= (1.f / 128.f); a1 *= (1.f / 128.f);
          asm volatile("" : "+f"(a0), "+f"(a1));
          bar_wg(wg);
          QSTEP(S0, dA0 + ((OFF_S + SLOT) >> 4), 1, wgmma_wait<0>());
          REL(ub + 376); ub += 8;
          SCHED_FENCE();
          float q0 = 0.f, q1 = 0.f;
          b0 = 0.f; b1 = 0.f;
#pragma unroll
          for (int i = 0; i < 64; i += 4) {
            const float d0 = S1[i] - a0, d1 = S1[i + 1] - a0, d2 = S1[i + 2] - a1, d3 = S1[i + 3] - a1;
            q0 = fmaf(d0, d0, q0); b0 = fmaf(d1, d1, b0); q1 = fmaf(d2, d2, q1); b1 = fmaf(d3, d3, b1);
          }
          q0 += b0; q1 += b1;
          q0 += __shfl_xor_sync(0xffffffffu, q0, 1); q1 += __shfl_xor_sync(0xffffffffu, q1, 1);
          q0 += __shfl_xor_sync(0xffffffffu, q0, 2); q1 += __shfl_xor_sync(0xffffffffu, q1, 2);
          if (t < 2) st_b64(g_stats + (size_t)(mm * 128 + r0 + g + t * 8) * 8 + jj, __float_as_uint(t ? a1 : a0), (__float_as_uint(t ? q1 : q0) & ~3u) | STAT_TAG(l));
        }
        if (l) { asm volatile("cp.async.bulk.wait_group 0;" ::: "memory"); bar_arrive<BAR_X1, 288>(); }
        ACC_DEF(S1, 96);
        QSTEP(S1, dA0 + (OFF_S >> 4), 0, {});
        QREL();
        QSTEP(S1, dA0 + ((OFF_S + SLOT) >> 4), 1, {});
        QREL();
#pragma unroll 1
        for (int i = 0; i < 14; i++) {
          QSTEP(S0, RA_CUR, 1, {});
          if (i == 0) PROF(2);
          QREL();
        }
      }
      LANE_CONSTS();
      mbar_wait(bar_stat, par);
      LNSTEP(S0, 0);
      wgmma_commit();
      const float rs0 = lds32f(sbase + OFF_ST + (r0 + g) * 4), rs1 = lds32f(sbase + OFF_ST + (r0 + g + 8) * 4);
      PUMP0();
      ACC_FENCE(S0, 96);
      PROF(3);
      if (!par) {
        constexpr uint32_t par = 0;
        uint32_t qa[16];
        uint32_t kf[32], vf[32];
#define DRAIN_A(ACC, hp, PMP) { \
          LANE_CONSTS(); \
          FRAG(kf + 16, ACC + 32, 0, (hp) * 2); \
          PMP; \
          FRAG(vf + 16, ACC + 64, 1, (hp) * 2 + 1); \
          _Pragma("unroll") for (int i_ = 0; i_ < 16; i_++) qa[i_] = pack_bf16(ACC[2 * i_], ACC[2 * i_ + 1]); \
          PINU(qa, 16); }
        DRAIN_A(S0, 0, PUMP0());
        if (l == 0 && NLAYERS > 1) {
#pragma unroll 1
          for (int rd = 1; rd >= 0; rd--) {
            FOLD(sbase + (12 - rd) * SLOT, rd);
            fence_proxy_async_smem();
            asm volatile("bar.arrive %0, 288;" :: "r"(BAR_WF + 1 - rd) : "memory");
          }
        }
        PUMPS(FPUMP);
        if (l == 0 && NLAYERS > 1) mbar_wait(bar_phi, 1);
#pragma unroll 1
        for (int h = 0; h < 2; h++) {
          const uint32_t pO = sbase + (h ? 3 : 12) * SLOT;
          PROF(4 + h * 12);
          LANE_CONSTS();
          FRAG_PUT(kf + 16, 10); FRAG_PUT(vf + 16, 11);
          STG_ARRIVE();
          if (h) { LOAD_X(); if (AW0) WSTEP(); } else PUMPS(HPUMP2);
          STG_WAIT();
          if (warp == 0) mbar_wait(bar_halo, h);
          FRAG_GET(kf, 10);
          PROF(5 + h * 12);
          float s[2][4][4];
#pragma unroll
          for (int ks = 0; ks < 2; ks++)
#pragma unroll
            for (int i = 0; i < 8; i++) {
              const int hh = (i >> 1) & 1, jb = (i & 1) + (~i >> 1 & 2);
              const uint32_t* b = kf + (jb >> 1) * 16 + hh * 8 + ks * 4 + (jb & 1) * 2;
              if (ks) mma_bf16(s[hh][jb], qa[hh * 8 + 4], qa[hh * 8 + 5], qa[hh * 8 + 6], qa[hh * 8 + 7], b[0], b[1]);
              else mma_bf16_z(s[hh][jb], qa[hh * 8], qa[hh * 8 + 1], qa[hh * 8 + 2], qa[hh * 8 + 3], b[0], b[1]);
            }
          PUMP();
          PROF(6 + h * 12);
          const bool e = g & 1, hb = (2 * t + (g & 1)) <= g;
          float va[2][2], vb[2][2], mx[2][2];
#pragma unroll
          for (int hh = 0; hh < 2; hh++) {
            va[hh][0] = e ? s[hh][1][1] : s[hh][1][0];
            vb[hh][0] = hb ? (e ? s[hh][2][1] : s[hh][2][0]) : (e ? s[hh][0][1] : s[hh][0][0]);
            va[hh][1] = e ? s[hh][2][3] : s[hh][2][2];
            vb[hh][1] = hb ? (e ? s[hh][3][3] : s[hh][3][2]) : (e ? s[hh][1][3] : s[hh][1][2]);
          }
          if (warp == 0 && mm == 0) {
#pragma unroll
            for (int hh = 0; hh < 2; hh++) { va[hh][0] = -INFINITY; if (!hb) { vb[hh][0] = -INFINITY; vb[hh][1] = -INFINITY; } }
          }
#pragma unroll
          for (int i = 0; i < 4; i++) mx[i >> 1][i & 1] = fmaxf(va[i >> 1][i & 1], vb[i >> 1][i & 1]);
#pragma unroll
          for (int o = 1; o <= 2; o <<= 1)
#pragma unroll
            for (int i = 0; i < 4; i++) mx[i >> 1][i & 1] = fmaxf(mx[i >> 1][i & 1], __shfl_xor_sync(0xffffffffu, mx[i >> 1][i & 1], o));
          const float sc0 = rs0 * (0.17677669529663687f * LOG2E), sc1 = rs1 * (0.17677669529663687f * LOG2E);
#pragma unroll
          for (int i = 0; i < 4; i++) {
            const float sc = (i & 1) ? sc1 : sc0, m = mx[i >> 1][i & 1];
            va[i >> 1][i & 1] = ex2((va[i >> 1][i & 1] - m) * sc); vb[i >> 1][i & 1] = ex2((vb[i >> 1][i & 1] - m) * sc);
            mx[i >> 1][i & 1] = va[i >> 1][i & 1] + vb[i >> 1][i & 1];
          }
          if (h == 0 && ASITE) { PIN(&va[0][0], 4); PIN(&vb[0][0], 4); PIN(&mx[0][0], 4); PUMP1(); }
          if (warp == 0) mbar_wait(bar_halo + 8, h);
          FRAG_GET(vf, 11);
#pragma unroll
          for (int o = 1; o <= 2; o <<= 1)
#pragma unroll
            for (int i = 0; i < 4; i++) mx[i >> 1][i & 1] += __shfl_xor_sync(0xffffffffu, mx[i >> 1][i & 1], o);
          const uint32_t selA = e ? 0x1044 : 0x4410, selB = e ? 0x3244 : 0x4432, selL = hb ? 0x4444 : selB, selH = hb ? selB : 0x4444;
          float o[2][4][4];
          uint32_t pa[2][8];
#pragma unroll
          for (int hh = 0; hh < 2; hh++) {
            const float i0 = rcp_fast(mx[hh][0]), i1 = rcp_fast(mx[hh][1]);
            const uint32_t w0 = pack_bf16(va[hh][0] * i0, vb[hh][0] * i0), w1 = pack_bf16(va[hh][1] * i1, vb[hh][1] * i1);
            pa[hh][0] = __byte_perm(w0, 0, selL); pa[hh][2] = __byte_perm(w0, 0, selA); pa[hh][3] = __byte_perm(w1, 0, selL);
            pa[hh][4] = __byte_perm(w0, 0, selH); pa[hh][5] = __byte_perm(w1, 0, selA); pa[hh][7] = __byte_perm(w1, 0, selH);
            pa[hh][1] = pa[hh][0] & pa[hh][4]; pa[hh][6] = pa[hh][3] & pa[hh][7];
          }
          PROF(7 + h * 12);
#pragma unroll
          for (int i = 0; i < 8; i++) mma_bf16_z(o[i >> 2][i & 3], pa[i >> 2][4], pa[i >> 2][5], pa[i >> 2][6], pa[i >> 2][7], vf[16 + 2 * i], vf[17 + 2 * i]);
#pragma unroll
          for (int i = 0; i < 8; i++) mma_bf16(o[i >> 2][i & 3], pa[i >> 2][0], pa[i >> 2][1], pa[i >> 2][2], pa[i >> 2][3], vf[2 * i], vf[2 * i + 1]);
          if (h == 0) PUMP1() else mbar_wait(bar_done + 30 * 8, par);
          if (NLAYERS > 1) mbar_wait(bar_phi + 8, 0);
#pragma unroll
          for (int i = 0; i < 4; i++) {
            const int hh = i >> 1, dp = i & 1;
            PMASKS(true, O_BIT(l));
            stsm_x4(pO + srowoff + ((hh * 64 + dp * 32 + lhi) ^ lsw), PBIT0(pack_bf16(o[hh][dp * 2][0], o[hh][dp * 2][1])), PBIT0(pack_bf16(o[hh][dp * 2][2], o[hh][dp * 2][3])),
                    PBIT1(pack_bf16(o[hh][dp * 2 + 1][0], o[hh][dp * 2 + 1][1])), PBIT1(pack_bf16(o[hh][dp * 2 + 1][2], o[hh][dp * 2 + 1][3])));
          }
          PUBLISH_O();
          PROF(11 + h * 12);
          if (h) break;
          REST_P1(ASKEW);
          asm volatile("cp.async.bulk.wait_group.read 0;" ::: "memory");
          DRAIN_A(S1, 1, {});
        }
      } else {
        constexpr uint32_t par = 1;
        float st[32];
        const float c0 = rs0 * LOG2E, c1 = rs1 * LOG2E;
        STAGE_V(S0 + 64, pV);
        if (warp < 2) sts128(sbase + OFF_ONES + warp * 512 + lane * 16, 0x3F803F80u, 0x3F803F80u, 0x3F803F80u, 0x3F803F80u);
        scale32(st, S0, c0, c1);
        PIN(st, 32);
#define KV_MMA(vs) { \
          const uint32_t dp = dA0 + 12 * 1024 - wg * 2560, dv = dA0 + (vs) * 1024 + ((OFF_ONES - (vs) * SLOT - 16) << 12) - wg * (512 << 16); \
          STG_WAIT(); \
          wgmma_fence(); \
          _Pragma("unroll") for (int ks = 0; ks < 8; ks++) { \
            const uint64_t a = DESC(dp + ks * 128, 0x40000040), b = DESC(dv + ks * (64 - (64 << 16)), 0x80000020); \
            if (ks == 0) wgmma_n40<0, 1>(kv, a, b); else wgmma_n40<1, 1>(kv, a, b); } \
          wgmma_commit(); }
#define KV_RED(hp) { \
          float* kvg = g_kv[l >> 1] + (jj * 4 + (hp) * 2) * KVH + warp * 768 + lane * 4; \
          _Pragma("unroll") for (int i = 0; i < 5; i++) red_v4(kvg + i * 128, kv[i * 3], kv[i * 3 + 1], kv[i * 3 + 2], 1.f); \
          red_v4(kvg + 640, kv[15], kv[16], kv[18], 1.f); }
#define KV_LOAD(hp) { \
          const uint4* kvg = reinterpret_cast<const uint4*>(g_kv[l >> 1] + (jj * 4 + (hp) * 2) * KVH) + warp * 192 + lane; \
          _Pragma("unroll") for (int i = 0; i < 6; i++) v[i] = ld_b128(kvg + i * 32); }
#define KVV(i) __uint_as_float((i) % 3 == 0 ? v[(i) / 3].x : ((i) % 3 == 1 ? v[(i) / 3].y : v[(i) / 3].z))
#define KV_TILE(hp) { \
          _Pragma("unroll 1") for (int it = 0; it < (1 << 16); it++) { \
            if (__all_sync(0xffffffffu, (v[0].w & v[1].w & v[2].w & v[3].w & v[4].w & v[5].w) == 0x41800000u)) break; \
            RETRY_COUNT(); \
            KV_LOAD(hp); \
          } \
          PROF(25 + (hp)); \
          const uint32_t e = lane & 7, jt = ((lane >> 1) & 4) + (e >> 1); \
          const uint32_t row = ((((warp >> 1) ^ wg) & 1) << 5) + ((jt & 1) << 4) + ((warp & 1) << 3) + (jt & 6) + (e & 1); \
          const uint32_t kd = pV + wg * 8192 + row * 128, ksw = (row & 7) << 4; \
          _Pragma("unroll") for (int i = 0; i < 2; i++) \
            stsm_x4(kd + ((i * 32 + lhi) ^ ksw), pack_bf16(KVV(i * 8), KVV(i * 8 + 1)), pack_bf16(KVV(i * 8 + 2), KVV(i * 8 + 3)), \
                    pack_bf16(KVV(i * 8 + 4), KVV(i * 8 + 5)), pack_bf16(KVV(i * 8 + 6), KVV(i * 8 + 7))); \
          stsm_x4(kd + ((64u + lhi) ^ ksw), pack_bf16(KVV(16), 1.f), pack_bf16(KVV(17), 1.f), 0u, 0u); }
#pragma unroll 1
        for (int h = 0; h < 2; h++) {
          PROF(4 + h * 2);
          SITE(0);
          LANE_CONSTS();
          const uint32_t dsw = (uint32_t)(g ^ (2 * t)) << 4, dst = ((t & 2) ? pK : sbase + 12 * SLOT) + (r0 + g) * 128;
          float e[16], f[16];
          float sa = exps16_<0>(e, st);
          exps16_fix<0>(e, st, sa);
          asm volatile("" : "+f"(sa)); PIN(e, 16); SITE(1);
          if (h) STG_WAIT();
          store16(e, sa, dst, dsw, 4);
          float sb = exps16_<1>(f, st);
          exps16_fix<1>(f, st, sb);
          asm volatile("" : "+f"(sb)); PIN(f, 16); SITE(2);
          store16(f, sb, dst, dsw, 0);
          float sc = exps16_<0>(e, st + 2);
          exps16_fix<0>(e, st + 2, sc);
          asm volatile("" : "+f"(sc)); PIN(e, 16); SITE(3);
          store16(e, sc, dst + 1024, dsw, 4);
          float sd = exps16_<1>(f, st + 2);
          exps16_fix<1>(f, st + 2, sd);
          asm volatile("" : "+f"(sd)); PIN(f, 16); SITE(4);
          store16(f, sd, dst + 1024, dsw, 0);
          PROF(5 + h * 2);
          if (h) break;
          {
            float kv[20];
            ACC_DEF(kv, 20);
            fence_proxy_async_smem();
            STG_ARRIVE();
            KV_MMA(11);
            PUMP0();
            ACC_FENCE(kv, 20);
            KV_RED(0);
            STG_ARRIVE();
          }
          scale32(st, S0 + 32, c0, c1);
          PIN(st, 32);
        }
        bool big;
        uint4 v[6];
        {
          float kv[20];
          if (KT0) { LANE_CONSTS(); KV_LOAD(0); }
          mbar_wait(bar_stat2, par);
          LNSTEP(S1, 1);
          ub = bar_full + 240;
          PUMP1();
          if (wg == 0) bar_sync<BAR_SKEW, 256>();
          QSTEP(S1, RA_CUR, 1, {});
          if (wg == 1) bar_arrive<BAR_SKEW, 256>();
          QREL();
          if (KT0 == 2) { LANE_CONSTS(); KV_TILE(0); }
          mbar_wait(bar_done + 30 * 8, par);
          wgmma_wait<0>();
          ACC_FENCE(S1, 96);
          if (!(RLATE & 2)) REL(bar_done + 31 * 8);
          PROF(13);
          LANE_CONSTS();
          STAGE_V(S1 + 64, sbase + 3 * SLOT);
          fence_proxy_async_smem();
          STG_ARRIVE();
          if (RLATE & 2) REL(bar_done + 31 * 8);
          scale32(st, S1, c0, c1);
          PIN(st, 32);
          PROF(16);
          ACC_DEF(kv, 20);
          KV_MMA(3);
          SCHED_FENCE();
          if (!KT0) KV_LOAD(0);
          big = any_big(st);
          SCHED_FENCE();
          wgmma_wait<0>();
          ACC_FENCE(kv, 20);
          KV_RED(1);
          PROF(17);
        }
#pragma unroll 1
        for (int h = 0; h < 2; h++) {
          const uint32_t pO = sbase + (h ? 3 : 8) * SLOT;
          LANE_CONSTS();
          uint32_t fq[32];
          expp16<0>(fq, st, big); expp16<1>(fq + 8, st, big); PINU(fq, 16);
          PROF(18 + h * 14);
          SCHED_FENCE();
          if (h) {
            asm volatile("cp.async.bulk.wait_group.read 0;" ::: "memory");
            mbar_wait(bar_lx, par);
          }
          if (h || KT0 < 2) {
            KV_TILE(h);
            fence_proxy_async_smem();
            STG_ARRIVE();
          }
          SCHED_FENCE();
          expp16<0>(fq + 16, st + 16, big); PINU(fq + 16, 8);
          if (h || KT0 < 2) STG_WAIT();
          wgmma_wait<0>();
          ACC_FENCE(S1, 64);
          PROF(19 + h * 14);
          float o[4][20];
#define O_MMA(hh) { \
            const uint64_t db = make_desc(pV + (hh) * 8192, 16, 1024); \
            ACC_DEF(o[(hh) * 2], 20); ACC_DEF(o[(hh) * 2 + 1], 20); \
            wgmma_fence(); \
            wgmma_n40_rs<0>(o[(hh) * 2], fq + (hh) * 16, db + 256); wgmma_n40_rs<0>(o[(hh) * 2 + 1], fq + (hh) * 16 + 8, db); \
            wgmma_n40_rs<1>(o[(hh) * 2], fq + (hh) * 16 + 4, db + 384); wgmma_n40_rs<1>(o[(hh) * 2 + 1], fq + (hh) * 16 + 12, db + 128); \
            wgmma_commit(); }
          O_MMA(0);
          SCHED_FENCE();
          expp16<1>(fq + 24, st + 16, big); PINU(fq + 24, 8);
          SCHED_FENCE();
          PMASKS(true, O_BIT(l));
#pragma unroll
          for (int hh = 0; hh < 2; hh++) {
            if (hh && !OW) O_MMA(1);
            wgmma_wait<0>();
            ACC_FENCE(o[hh * 2], 20); ACC_FENCE(o[hh * 2 + 1], 20);
            if (!hh && OW) { O_MMA(1); SCHED_FENCE(); }
            const float* x = o[hh * 2];
            const float* y = o[hh * 2 + 1];
            const float rx0 = rcp_fast(x[17]), ry0 = rcp_fast(y[17]), rx1 = rcp_fast(x[19]), ry1 = rcp_fast(y[19]);
            const float i0 = rcp_fast(fmaf(x[16], rx0, y[16] * ry0) + 1e-6f), i1 = rcp_fast(fmaf(x[18], rx1, y[18] * ry1) + 1e-6f);
            const float ax0 = rx0 * i0, ay0 = ry0 * i0, ax1 = rx1 * i1, ay1 = ry1 * i1;
#pragma unroll
            for (int dp = 0; dp < 2; dp++)
              stsm_x4(pO + srowoff + ((hh * 64 + dp * 32 + lhi) ^ lsw),
                      PBIT0(pack_bf16(fmaf(x[dp * 8], ax0, y[dp * 8] * ay0), fmaf(x[dp * 8 + 1], ax0, y[dp * 8 + 1] * ay0))),
                      PBIT0(pack_bf16(fmaf(x[dp * 8 + 2], ax1, y[dp * 8 + 2] * ay1), fmaf(x[dp * 8 + 3], ax1, y[dp * 8 + 3] * ay1))),
                      PBIT1(pack_bf16(fmaf(x[dp * 8 + 4], ax0, y[dp * 8 + 4] * ay0), fmaf(x[dp * 8 + 5], ax0, y[dp * 8 + 5] * ay0))),
                      PBIT1(pack_bf16(fmaf(x[dp * 8 + 6], ax1, y[dp * 8 + 6] * ay1), fmaf(x[dp * 8 + 7], ax1, y[dp * 8 + 7] * ay1))));
          }
          PUBLISH_O();
          PROF(20 + h * 14);
          if (h) break;
          scale32(st, S1 + 32, c0, c1);
          PIN(st, 32);
          LOAD_X();
          bar_wg(wg);
          WSTEP();
          SCHED_FENCE();
          if (KVL == 0) KV_LOAD(1);
          big = any_big(st);
          if (KVL == 1) { SCHED_FENCE(); KV_LOAD(1); }
          PROF(31);
        }
      }
      __syncwarp();
      if (elect_one()) mbar_arrive_local(bar_epi);
      bar_wg(wg);
#pragma unroll 1
      while (ub < bar_full + 384) {
        WSTEP();
        if (ub == bar_full + 8 * 41) { asm volatile("cp.async.bulk.wait_group.read 0;" ::: "memory"); PROF(35); }
        if (ub == bar_full + 8 * 42) PROF(36);
      }
      wgmma_wait<0>();
      ACC_FENCE(S1, 64);
      if (!RLATE) REL(bar_done + 47 * 8);
      PROF(37);
      {
        LANE_CONSTS();
        X_OUT(0, l < NLAYERS - 1);
        WARP_STORE(l < NLAYERS - 1 ? &tm_os : &tm_xo, pK, jj * 128, mm * 128 + (l < NLAYERS - 1 ? S_LEN : 0));
        if (RLATE) REL(bar_done + 47 * 8);
        if (l == NLAYERS - 1) {
          X_OUT(1, false);
          WARP_STORE(&tm_xo, pV, jj * 128 + 64, mm * 128);
          asm volatile("cp.async.bulk.wait_group 0;" ::: "memory");
        }
      }
#pragma unroll
      for (int i = 32; i < 64; i++) { uint32_t c; asm volatile("mov.b32 %0, %1;" : "=r"(c) : "f"(S1[i])); S1[i] = __uint_as_float(c); }
      PROF(38);
    }
    const int tid = threadIdx.x;
    if (tid == 0) {
      unsigned old = atomicAdd(&g_flags.done.v, 1);
      if (old == ep1 * NMAIN - 1) {
        asm volatile("st.relaxed.gpu.global.u32 [%0], %1;" :: "l"(&g_flags.epoch.v), "r"(ep1) : "memory");
      }
    }
    __syncwarp();
    cluster_sync();
  }
}

typedef CUresult (*PFN_encode)(CUtensorMap*, CUtensorMapDataType, cuuint32_t, void*, const cuuint64_t*, const cuuint64_t*,
                               const cuuint32_t*, const cuuint32_t*, CUtensorMapInterleave, CUtensorMapSwizzle,
                               CUtensorMapL2promotion, CUtensorMapFloatOOBfill);

CUtensorMap make_map(PFN_encode enc, const void* ptr, uint64_t inner, uint64_t outer, uint32_t box_inner, uint32_t box_outer,
                     CUtensorMapSwizzle swz = CU_TENSOR_MAP_SWIZZLE_128B) {
  CUtensorMap m;
  cuuint64_t dims[2] = {inner, outer};
  cuuint64_t strides[1] = {inner * 2};
  cuuint32_t box[2] = {box_inner, box_outer};
  cuuint32_t es[2] = {1, 1};
  enc(&m, CU_TENSOR_MAP_DATA_TYPE_BFLOAT16, 2, const_cast<void*>(ptr), dims, strides, box, es, CU_TENSOR_MAP_INTERLEAVE_NONE,
      swz, CU_TENSOR_MAP_L2_PROMOTION_L2_256B, CU_TENSOR_MAP_FLOAT_OOB_FILL_NONE);
  return m;
}

}

extern "C" void kernel_launch(void* const* d_in, const int* in_sizes, int n_in, void* d_out, int out_size) {
  (void)in_sizes; (void)n_in; (void)out_size;
  static PFN_encode enc = nullptr;
  if (!enc) {
    void* fn = nullptr;
    cudaDriverEntryPointQueryResult qr;
    cudaGetDriverEntryPoint("cuTensorMapEncodeTiled", &fn, cudaEnableDefault, &qr);
    enc = (PFN_encode)fn;
    cudaFuncSetAttribute(mega_kernel, cudaFuncAttributeMaxDynamicSharedMemorySize, SMEM_BYTES);
  }
  Params prm;
  prm.x0 = (const __nv_bfloat16*)d_in[0];
  prm.wA_qkv = (const __nv_bfloat16*)d_in[1];
  prm.wA_o = (const __nv_bfloat16*)d_in[2];
  prm.wB_qkv = (const __nv_bfloat16*)d_in[4];
  prm.wB_phi = (const __nv_bfloat16*)d_in[5];
  prm.wB_o = (const __nv_bfloat16*)d_in[6];
  prm.out = (__nv_bfloat16*)d_out;
  void *obuf = nullptr, *wf = nullptr;
  cudaGetSymbolAddress(&obuf, g_obuf);
  cudaGetSymbolAddress(&wf, g_wfold);
  CUtensorMap tm_x0 = make_map(enc, d_in[0], D_MODEL, S_LEN, 64, 128);
  CUtensorMap tm_xo = make_map(enc, d_out, D_MODEL, S_LEN, 64, 16);
  CUtensorMap tm_os = make_map(enc, obuf, D_MODEL, 2 * S_LEN, 64, 16);
  CUtensorMap tm_o = make_map(enc, obuf, D_MODEL, 2 * S_LEN, 64, 128);
  CUtensorMap tm_wf = make_map(enc, wf, 2048, D_MODEL, 64, 32);
  CUtensorMap tm_wqA = make_map(enc, d_in[1], 3 * D_MODEL, D_MODEL, 64, 32);
  CUtensorMap tm_wqB = make_map(enc, prm.wB_qkv, 3 * D_MODEL, D_MODEL, 64, 32);
  CUtensorMap tm_woA = make_map(enc, prm.wA_o, D_MODEL, D_MODEL, 64, 64);
  CUtensorMap tm_woB = make_map(enc, prm.wB_o, D_MODEL, D_MODEL, 64, 64);
  CUtensorMap tm_phi = make_map(enc, prm.wB_phi, 32, 1024, 32, 128, CU_TENSOR_MAP_SWIZZLE_64B);
  mega_kernel<<<NMAIN + NAUX, 384, SMEM_BYTES>>>(tm_x0, tm_xo, tm_os, tm_o, tm_wf, tm_wqA, tm_wqB, tm_woA, tm_woB, tm_phi, prm);
}
```

```cpp
#include <cuda_runtime.h>
#include <cuda.h>
#include <cuda_bf16.h>
#include <stdint.h>

#define NLAYERS 4

#define STAG1 0
#define HPUMP1 2
#define HPUMP2 1
#define ASKEW 2
#define FPUMP 3
#define PFGAP 100
#define POLLGAP 120
#define OW 1
#define AW0 1
#define RLATE 3
#define FSTART 0
#define MAPV 1
#define HW1 29
#define XPACE 0x06050401000000ull
#define XP0 4
#define HW0 18
#define XD 4
#define WFGAP 50
#define KT0 2
#define W23 0
#define AX 0
#define PF0 1
#define EARLY 2
#define BIGLIM 60.f
#define SUMLO 0x1p-100f
#define SUMHI 0x1p100f
#define EROT 1
#define FINW 0
#define AHOIST 1
#define KVL 1
#define BMASK 0x1F
#define ASITE 1
namespace {

constexpr int S_LEN = 2048, D_MODEL = 1024;
constexpr int NAUX = 4, NMAIN = 128;
constexpr int SLOT = 16384;
constexpr int QST = 24576;
constexpr int OFF_RA = 6 * SLOT, OFF_S = 10 * SLOT;
constexpr int OFF_HALO = 13 * SLOT, OFF_LNB = OFF_HALO  , OFF_ONES = OFF_HALO + 3072;
constexpr int OFF_ST = OFF_HALO + 7168  , OFF_PHI = OFF_HALO + 8192;
constexpr int OFF_BAR = 14 * SLOT;
constexpr int OFF_LNA = OFF_BAR + 1024;
constexpr int SMEM_BYTES = OFF_LNA + 2048;
#define WO_ASLOT(par) ((par) ? 0x9876CAB39876CA98ull : 0x98C76BA398C7698Cull)
constexpr unsigned long long WO_BSLOT = 0x5432105421054210ull;
__device__ __forceinline__ int srcb(int j, int i) { return (i + (i >= j)) & 7; }
__device__ __forceinline__ int kslice(int j, int i) { return i < 2 ? 2 * j + i : (i < 9 ? 2 * srcb(j, i - 2) : 2 * srcb(j, i - 9) + 1); }
__device__ __forceinline__ int wslice(int j, int s) { return 2 * ((s & 7) ? srcb(j, (s & 7) - 1) : j) + (s >> 3); }
constexpr int KVH = 6 * 128 * 4;

struct __align__(128) Flag { unsigned v; unsigned pad[31]; };
struct Flags {
  Flag xready[4][16];
  Flag wfready[8];
  Flag done;
  Flag epoch;
};

__device__ Flags g_flags;
__device__ __nv_bfloat16 g_obuf[2 * S_LEN * D_MODEL];
#define O_BIT(l) ((epoch * NLAYERS + (l) + 1) & 1u)
#define X_BIT(l) ((epoch * (NLAYERS - 1) + (l) + 1) & 1u)
__device__ __nv_bfloat16 g_wfold[D_MODEL * 2048];
__device__ uint4 g_halo[16 * 8 * 512];
__device__ __align__(128) float g_kv[2][32 * KVH];
__device__ __align__(128) uint2 g_colsum[2][1536][2];
__device__ __align__(128) uint2 g_stats[S_LEN * 8];
#define H_BIT(l) (NLAYERS > 2 ? (uint32_t)((l) == 0) : (ep1 & 1))
#define STAT_TAG(l) ((ep1 * NLAYERS + (l) + 1) & 3u)

#define RETRY_COUNT()
#define PRL 0
#define PRU 0
#define PROFL 1
#define PROFW 0
#define PROFT(i) do {} while (0)
#define PROF(i) do {} while (0)

__device__ __forceinline__ uint32_t smem_u32(const void* p) { return (uint32_t)__cvta_generic_to_shared(p); }
__device__ __forceinline__ bool elect_one() {
  uint32_t p;
  asm volatile("{\n.reg .pred p;\nelect.sync _|p, 0xffffffff;\nselp.u32 %0, 1, 0, p;\n}\n" : "=r"(p));
  return p != 0;
}
__device__ __forceinline__ void mbar_init(uint32_t bar, uint32_t cnt) {
  asm volatile("mbarrier.init.shared::cta.b64 [%0], %1;" :: "r"(bar), "r"(cnt));
}
__device__ __forceinline__ void mbar_expect_tx(uint32_t bar, uint32_t bytes) {
  asm volatile("mbarrier.arrive.expect_tx.shared::cta.b64 _, [%0], %1;" :: "r"(bar), "r"(bytes) : "memory");
}
#define mbar_wait(bar, parity) \
  asm volatile("{\n.reg .pred p, q;\nW_%=:\nmbarrier.try_wait.parity.shared::cta.b64 p, [%1], %2;\nadd.s32 %0, %0, -1;\n" \
               "setp.gt.and.s32 q, %0, 0, !p;\n@q bra.uni W_%=;\n}\n" : "+r"(budget) : "r"((uint32_t)(bar)), "r"((uint32_t)(parity)) : "memory")
#define mbar_wait_sl(bar, parity) \
  asm volatile("{\n.reg .pred p, q;\nW_%=:\nmbarrier.try_wait.parity.shared::cta.b64 p, [%1], %2, 20000;\nadd.s32 %0, %0, -64;\n" \
               "setp.gt.and.s32 q, %0, 0, !p;\n@q bra.uni W_%=;\n}\n" : "+r"(budget) : "r"((uint32_t)(bar)), "r"((uint32_t)(parity)) : "memory")
__device__ __forceinline__ void mbar_arrive_local(uint32_t bar) {
  asm volatile("mbarrier.arrive.shared::cta.b64 _, [%0];" :: "r"(bar) : "memory");
}
__device__ __forceinline__ void tma_load_2d(uint32_t dst, const CUtensorMap* tm, uint32_t bar, int c0, int c1) {
  asm volatile("cp.async.bulk.tensor.2d.shared::cluster.global.mbarrier::complete_tx::bytes [%0], [%1, {%3, %4}], [%2];"
               :: "r"(dst), "l"(tm), "r"(bar), "r"(c0), "r"(c1) : "memory");
}
__device__ __forceinline__ void tma_load_2d_mc(uint32_t dst, const CUtensorMap* tm, uint32_t bar, int c0, int c1) {
  asm volatile("cp.async.bulk.tensor.2d.shared::cluster.global.mbarrier::complete_tx::bytes.multicast::cluster [%0], [%1, {%3, %4}], [%2], %5;"
               :: "r"(dst), "l"(tm), "r"(bar), "r"(c0), "r"(c1), "h"((uint16_t)3) : "memory");
}
__device__ __forceinline__ void tma_store_2d(const CUtensorMap* tm, uint32_t src, int c0, int c1) {
  asm volatile("cp.async.bulk.tensor.2d.global.shared::cta.bulk_group [%0, {%2, %3}], [%1];"
               :: "l"(tm), "r"(src), "r"(c0), "r"(c1) : "memory");
}
__device__ __forceinline__ void bulk_commit_wait() {
  asm volatile("cp.async.bulk.commit_group;\ncp.async.bulk.wait_group 0;" ::: "memory");
}
__device__ __forceinline__ void prefetch_tmap(const CUtensorMap* tm) {
  asm volatile("prefetch.tensormap [%0];" :: "l"(tm) : "memory");
}
__device__ __forceinline__ void fence_proxy_async_global() { asm volatile("fence.proxy.async.global;" ::: "memory"); }
__device__ __forceinline__ void fence_proxy_async_smem() { asm volatile("fence.proxy.async.shared::cta;" ::: "memory"); }
__device__ __forceinline__ unsigned ld_relaxed(const unsigned* p) {
  unsigned v;
  asm volatile("ld.relaxed.gpu.global.u32 %0, [%1];" : "=r"(v) : "l"(p) : "memory");
  return v;
}
__device__ __forceinline__ void fence_acquire() { asm volatile("fence.acquire.gpu;" ::: "memory"); }
__device__ __forceinline__ void wait_flag(const unsigned* p, unsigned target) {
  int it = 0;
  while ((int)(ld_relaxed(p) - target) < 0 && ++it < (1 << 20)) {}
  fence_acquire();
}
__device__ __forceinline__ void signal_release(unsigned* p) {
  asm volatile("red.release.gpu.global.add.u32 [%0], 1;" :: "l"(p) : "memory");
}
template <int ID, int N> __device__ __forceinline__ void bar_arrive() { asm volatile("bar.arrive %0, %1;" :: "n"(ID), "n"(N) : "memory"); }
template <int ID, int N> __device__ __forceinline__ void bar_sync() { asm volatile("bar.sync %0, %1;" :: "n"(ID), "n"(N) : "memory"); }
__device__ __forceinline__ void bar_wg(int wg) { asm volatile("bar.sync %0, 128;" :: "r"(2 + wg) : "memory"); }
__device__ __forceinline__ void cluster_sync() {
  asm volatile("barrier.cluster.arrive.relaxed.aligned;\nbarrier.cluster.wait.aligned;" ::: "memory");
}
__device__ __forceinline__ void cluster_wait() { asm volatile("barrier.cluster.wait.acquire.aligned;" ::: "memory"); }
enum { BAR_X1 = 7, BAR_WF = 8  , BAR_SKEW = 10 };

__device__ __forceinline__ void wgmma_fence() { asm volatile("wgmma.fence.sync.aligned;" ::: "memory"); }
__device__ __forceinline__ void wgmma_commit() { asm volatile("wgmma.commit_group.sync.aligned;" ::: "memory"); }
template <int N> __device__ __forceinline__ void wgmma_wait() { asm volatile("wgmma.wait_group.sync.aligned %0;" :: "n"(N) : "memory"); }

template <int scale_d, int tnsp_b = 1> __device__ __forceinline__ void wgmma_n192(float* d, uint64_t descA, uint64_t descB) {
  asm volatile("{\n.reg .pred p;\nsetp.ne.b32 p, %98, 0;\n"
               "wgmma.mma_async.sync.aligned.m64n192k16.f32.bf16.bf16 {%0,%1,%2,%3,%4,%5,%6,%7,%8,%9,%10,%11,%12,%13,%14,%15,%16,%17,%18,%19,%20,%21,%22,%23,%24,%25,%26,%27,%28,%29,%30,%31,%32,%33,%34,%35,%36,%37,%38,%39,%40,%41,%42,%43,%44,%45,%46,%47,%48,%49,%50,%51,%52,%53,%54,%55,%56,%57,%58,%59,%60,%61,%62,%63,%64,%65,%66,%67,%68,%69,%70,%71,%72,%73,%74,%75,%76,%77,%78,%79,%80,%81,%82,%83,%84,%85,%86,%87,%88,%89,%90,%91,%92,%93,%94,%95}, %96, %97, p, 1, 1, 0, %99;\n}\n"
               : "+f"(d[0]), "+f"(d[1]), "+f"(d[2]), "+f"(d[3]), "+f"(d[4]), "+f"(d[5]), "+f"(d[6]), "+f"(d[7]), "+f"(d[8]), "+f"(d[9]), "+f"(d[10]), "+f"(d[11]), "+f"(d[12]), "+f"(d[13]), "+f"(d[14]), "+f"(d[15]), "+f"(d[16]), "+f"(d[17]), "+f"(d[18]), "+f"(d[19]), "+f"(d[20]), "+f"(d[21]), "+f"(d[22]), "+f"(d[23]), "+f"(d[24]), "+f"(d[25]), "+f"(d[26]), "+f"(d[27]), "+f"(d[28]), "+f"(d[29]), "+f"(d[30]), "+f"(d[31]), "+f"(d[32]), "+f"(d[33]), "+f"(d[34]), "+f"(d[35]), "+f"(d[36]), "+f"(d[37]), "+f"(d[38]), "+f"(d[39]), "+f"(d[40]), "+f"(d[41]), "+f"(d[42]), "+f"(d[43]), "+f"(d[44]), "+f"(d[45]), "+f"(d[46]), "+f"(d[47]), "+f"(d[48]), "+f"(d[49]), "+f"(d[50]), "+f"(d[51]), "+f"(d[52]), "+f"(d[53]), "+f"(d[54]), "+f"(d[55]), "+f"(d[56]), "+f"(d[57]), "+f"(d[58]), "+f"(d[59]), "+f"(d[60]), "+f"(d[61]), "+f"(d[62]), "+f"(d[63]), "+f"(d[64]), "+f"(d[65]), "+f"(d[66]), "+f"(d[67]), "+f"(d[68]), "+f"(d[69]), "+f"(d[70]), "+f"(d[71]), "+f"(d[72]), "+f"(d[73]), "+f"(d[74]), "+f"(d[75]), "+f"(d[76]), "+f"(d[77]), "+f"(d[78]), "+f"(d[79]), "+f"(d[80]), "+f"(d[81]), "+f"(d[82]), "+f"(d[83]), "+f"(d[84]), "+f"(d[85]), "+f"(d[86]), "+f"(d[87]), "+f"(d[88]), "+f"(d[89]), "+f"(d[90]), "+f"(d[91]), "+f"(d[92]), "+f"(d[93]), "+f"(d[94]), "+f"(d[95])
               : "l"(descA), "l"(descB), "n"(scale_d), "n"(tnsp_b));
}
template <int scale_d> __device__ __forceinline__ void wgmma4_n192(float* d, uint32_t da, uint32_t db) {
#define R_ "{%0,%1,%2,%3,%4,%5,%6,%7,%8,%9,%10,%11,%12,%13,%14,%15,%16,%17,%18,%19,%20,%21,%22,%23,%24,%25,%26,%27,%28,%29,%30,%31,%32,%33,%34,%35,%36,%37,%38,%39,%40,%41,%42,%43,%44,%45,%46,%47,%48,%49,%50,%51,%52,%53,%54,%55,%56,%57,%58,%59,%60,%61,%62,%63,%64,%65,%66,%67,%68,%69,%70,%71,%72,%73,%74,%75,%76,%77,%78,%79,%80,%81,%82,%83,%84,%85,%86,%87,%88,%89,%90,%91,%92,%93,%94,%95}"
  asm volatile("{\n.reg .pred p, q;\n.reg .b64 a, b;\nsetp.ne.b32 p, %98, 0;\nsetp.eq.b32 q, 0, 0;\nmov.b64 a, {%96, 0x40000040};\nmov.b64 b, {%97, 0x40000040};\n"
               "wgmma.mma_async.sync.aligned.m64n192k16.f32.bf16.bf16 " R_ ", a, b, p, 1, 1, 0, 1;\nadd.s64 a, a, 2;\nadd.s64 b, b, 128;\n"
               "wgmma.mma_async.sync.aligned.m64n192k16.f32.bf16.bf16 " R_ ", a, b, q, 1, 1, 0, 1;\nadd.s64 a, a, 2;\nadd.s64 b, b, 128;\n"
               "wgmma.mma_async.sync.aligned.m64n192k16.f32.bf16.bf16 " R_ ", a, b, q, 1, 1, 0, 1;\nadd.s64 a, a, 2;\nadd.s64 b, b, 128;\n"
               "wgmma.mma_async.sync.aligned.m64n192k16.f32.bf16.bf16 " R_ ", a, b, q, 1, 1, 0, 1;\n}\n"
               : "+f"(d[0]), "+f"(d[1]), "+f"(d[2]), "+f"(d[3]), "+f"(d[4]), "+f"(d[5]), "+f"(d[6]), "+f"(d[7]), "+f"(d[8]), "+f"(d[9]), "+f"(d[10]), "+f"(d[11]), "+f"(d[12]), "+f"(d[13]), "+f"(d[14]), "+f"(d[15]), "+f"(d[16]), "+f"(d[17]), "+f"(d[18]), "+f"(d[19]), "+f"(d[20]), "+f"(d[21]), "+f"(d[22]), "+f"(d[23]), "+f"(d[24]), "+f"(d[25]), "+f"(d[26]), "+f"(d[27]), "+f"(d[28]), "+f"(d[29]), "+f"(d[30]), "+f"(d[31]), "+f"(d[32]), "+f"(d[33]), "+f"(d[34]), "+f"(d[35]), "+f"(d[36]), "+f"(d[37]), "+f"(d[38]), "+f"(d[39]), "+f"(d[40]), "+f"(d[41]), "+f"(d[42]), "+f"(d[43]), "+f"(d[44]), "+f"(d[45]), "+f"(d[46]), "+f"(d[47]), "+f"(d[48]), "+f"(d[49]), "+f"(d[50]), "+f"(d[51]), "+f"(d[52]), "+f"(d[53]), "+f"(d[54]), "+f"(d[55]), "+f"(d[56]), "+f"(d[57]), "+f"(d[58]), "+f"(d[59]), "+f"(d[60]), "+f"(d[61]), "+f"(d[62]), "+f"(d[63]), "+f"(d[64]), "+f"(d[65]), "+f"(d[66]), "+f"(d[67]), "+f"(d[68]), "+f"(d[69]), "+f"(d[70]), "+f"(d[71]), "+f"(d[72]), "+f"(d[73]), "+f"(d[74]), "+f"(d[75]), "+f"(d[76]), "+f"(d[77]), "+f"(d[78]), "+f"(d[79]), "+f"(d[80]), "+f"(d[81]), "+f"(d[82]), "+f"(d[83]), "+f"(d[84]), "+f"(d[85]), "+f"(d[86]), "+f"(d[87]), "+f"(d[88]), "+f"(d[89]), "+f"(d[90]), "+f"(d[91]), "+f"(d[92]), "+f"(d[93]), "+f"(d[94]), "+f"(d[95])
               : "r"(da), "r"(db), "n"(scale_d));
#undef R_
}
template <int scale_d> __device__ __forceinline__ void wgmma4_n128(float* d, uint32_t da, uint32_t db) {
#define R_ "{%0,%1,%2,%3,%4,%5,%6,%7,%8,%9,%10,%11,%12,%13,%14,%15,%16,%17,%18,%19,%20,%21,%22,%23,%24,%25,%26,%27,%28,%29,%30,%31,%32,%33,%34,%35,%36,%37,%38,%39,%40,%41,%42,%43,%44,%45,%46,%47,%48,%49,%50,%51,%52,%53,%54,%55,%56,%57,%58,%59,%60,%61,%62,%63}"
  asm volatile("{\n.reg .pred p, q;\n.reg .b64 a, b;\nsetp.ne.b32 p, %66, 0;\nsetp.eq.b32 q, 0, 0;\nmov.b64 a, {%64, 0x40000040};\nmov.b64 b, {%65, 0x40000040};\n"
               "wgmma.mma_async.sync.aligned.m64n128k16.f32.bf16.bf16 " R_ ", a, b, p, 1, 1, 0, 1;\nadd.s64 a, a, 2;\nadd.s64 b, b, 128;\n"
               "wgmma.mma_async.sync.aligned.m64n128k16.f32.bf16.bf16 " R_ ", a, b, q, 1, 1, 0, 1;\nadd.s64 a, a, 2;\nadd.s64 b, b, 128;\n"
               "wgmma.mma_async.sync.aligned.m64n128k16.f32.bf16.bf16 " R_ ", a, b, q, 1, 1, 0, 1;\nadd.s64 a, a, 2;\nadd.s64 b, b, 128;\n"
               "wgmma.mma_async.sync.aligned.m64n128k16.f32.bf16.bf16 " R_ ", a, b, q, 1, 1, 0, 1;\n}\n"
               : "+f"(d[0]), "+f"(d[1]), "+f"(d[2]), "+f"(d[3]), "+f"(d[4]), "+f"(d[5]), "+f"(d[6]), "+f"(d[7]), "+f"(d[8]), "+f"(d[9]), "+f"(d[10]), "+f"(d[11]), "+f"(d[12]), "+f"(d[13]), "+f"(d[14]), "+f"(d[15]), "+f"(d[16]), "+f"(d[17]), "+f"(d[18]), "+f"(d[19]), "+f"(d[20]), "+f"(d[21]), "+f"(d[22]), "+f"(d[23]), "+f"(d[24]), "+f"(d[25]), "+f"(d[26]), "+f"(d[27]), "+f"(d[28]), "+f"(d[29]), "+f"(d[30]), "+f"(d[31]), "+f"(d[32]), "+f"(d[33]), "+f"(d[34]), "+f"(d[35]), "+f"(d[36]), "+f"(d[37]), "+f"(d[38]), "+f"(d[39]), "+f"(d[40]), "+f"(d[41]), "+f"(d[42]), "+f"(d[43]), "+f"(d[44]), "+f"(d[45]), "+f"(d[46]), "+f"(d[47]), "+f"(d[48]), "+f"(d[49]), "+f"(d[50]), "+f"(d[51]), "+f"(d[52]), "+f"(d[53]), "+f"(d[54]), "+f"(d[55]), "+f"(d[56]), "+f"(d[57]), "+f"(d[58]), "+f"(d[59]), "+f"(d[60]), "+f"(d[61]), "+f"(d[62]), "+f"(d[63])
               : "r"(da), "r"(db), "n"(scale_d));
#undef R_
}
template <int scale_d> __device__ __forceinline__ void wgmma_n32(float* d, uint64_t descA, uint64_t descB) {
  asm volatile("{\n.reg .pred p;\nsetp.ne.b32 p, %18, 0;\n"
               "wgmma.mma_async.sync.aligned.m64n32k16.f32.bf16.bf16 {%0,%1,%2,%3,%4,%5,%6,%7,%8,%9,%10,%11,%12,%13,%14,%15}, %16, %17, p, 1, 1, 0, 1;\n}\n"
               : "+f"(d[0]), "+f"(d[1]), "+f"(d[2]), "+f"(d[3]), "+f"(d[4]), "+f"(d[5]), "+f"(d[6]), "+f"(d[7]), "+f"(d[8]), "+f"(d[9]), "+f"(d[10]), "+f"(d[11]), "+f"(d[12]), "+f"(d[13]), "+f"(d[14]), "+f"(d[15])
               : "l"(descA), "l"(descB), "n"(scale_d));
}
template <int scale_d, int tnsp_a> __device__ __forceinline__ void wgmma_n40(float* d, uint64_t descA, uint64_t descB) {
  asm volatile("{\n.reg .pred p;\nsetp.ne.b32 p, %22, 0;\n"
               "wgmma.mma_async.sync.aligned.m64n40k16.f32.bf16.bf16 {%0,%1,%2,%3,%4,%5,%6,%7,%8,%9,%10,%11,%12,%13,%14,%15,%16,%17,%18,%19}, %20, %21, p, 1, 1, %23, 1;\n}\n"
               : "+f"(d[0]), "+f"(d[1]), "+f"(d[2]), "+f"(d[3]), "+f"(d[4]), "+f"(d[5]), "+f"(d[6]), "+f"(d[7]), "+f"(d[8]), "+f"(d[9]), "+f"(d[10]), "+f"(d[11]), "+f"(d[12]), "+f"(d[13]), "+f"(d[14]), "+f"(d[15]), "+f"(d[16]), "+f"(d[17]), "+f"(d[18]), "+f"(d[19])
               : "l"(descA), "l"(descB), "n"(scale_d), "n"(tnsp_a));
}
template <int scale_d> __device__ __forceinline__ void wgmma_n40_rs(float* d, const uint32_t* a, uint64_t descB) {
  asm volatile("{\n.reg .pred p;\nsetp.ne.b32 p, %25, 0;\n"
               "wgmma.mma_async.sync.aligned.m64n40k16.f32.bf16.bf16 {%0,%1,%2,%3,%4,%5,%6,%7,%8,%9,%10,%11,%12,%13,%14,%15,%16,%17,%18,%19}, {%20,%21,%22,%23}, %24, p, 1, 1, 1;\n}\n"
               : "+f"(d[0]), "+f"(d[1]), "+f"(d[2]), "+f"(d[3]), "+f"(d[4]), "+f"(d[5]), "+f"(d[6]), "+f"(d[7]), "+f"(d[8]), "+f"(d[9]), "+f"(d[10]), "+f"(d[11]), "+f"(d[12]), "+f"(d[13]), "+f"(d[14]), "+f"(d[15]), "+f"(d[16]), "+f"(d[17]), "+f"(d[18]), "+f"(d[19])
               : "r"(a[0]), "r"(a[1]), "r"(a[2]), "r"(a[3]), "l"(descB), "n"(scale_d));
}
__device__ __forceinline__ uint64_t make_desc(uint32_t addr, uint32_t lbo_bytes, uint32_t sbo_bytes) {
  return (uint64_t)((addr & 0x3FFFF) >> 4) | ((uint64_t)(lbo_bytes >> 4) << 16) | ((uint64_t)(sbo_bytes >> 4) << 32) | (1ull << 62);
}

__device__ __forceinline__ void ldsm_x4(uint32_t addr, uint32_t& r0, uint32_t& r1, uint32_t& r2, uint32_t& r3) {
  asm volatile("ldmatrix.sync.aligned.m8n8.x4.shared.b16 {%0,%1,%2,%3}, [%4];" : "=r"(r0), "=r"(r1), "=r"(r2), "=r"(r3) : "r"(addr) : "memory");
}
__device__ __forceinline__ void ldsm_x4_t(uint32_t addr, uint32_t& r0, uint32_t& r1, uint32_t& r2, uint32_t& r3) {
  asm volatile("ldmatrix.sync.aligned.m8n8.x4.trans.shared.b16 {%0,%1,%2,%3}, [%4];" : "=r"(r0), "=r"(r1), "=r"(r2), "=r"(r3) : "r"(addr) : "memory");
}
__device__ __forceinline__ void stsm_x4(uint32_t addr, uint32_t r0, uint32_t r1, uint32_t r2, uint32_t r3) {
  asm volatile("stmatrix.sync.aligned.m8n8.x4.shared.b16 [%0], {%1,%2,%3,%4};" :: "r"(addr), "r"(r0), "r"(r1), "r"(r2), "r"(r3) : "memory");
}
__device__ __forceinline__ void sts128(uint32_t addr, uint32_t a, uint32_t b, uint32_t c, uint32_t d) {
  asm volatile("st.shared.v4.u32 [%0], {%1,%2,%3,%4};" :: "r"(addr), "r"(a), "r"(b), "r"(c), "r"(d) : "memory");
}
__device__ __forceinline__ float lds32f(uint32_t addr) {
  float v;
  asm volatile("ld.shared.f32 %0, [%1];" : "=f"(v) : "r"(addr) : "memory");
  return v;
}
__device__ __forceinline__ void sts32f(uint32_t addr, float a) {
  asm volatile("st.shared.f32 [%0], %1;" :: "r"(addr), "f"(a) : "memory");
}
__device__ __forceinline__ void mma_bf16(float (&c)[4], uint32_t a0, uint32_t a1, uint32_t a2, uint32_t a3, uint32_t b0, uint32_t b1) {
  asm volatile("mma.sync.aligned.m16n8k16.row.col.f32.bf16.bf16.f32 {%0,%1,%2,%3}, {%4,%5,%6,%7}, {%8,%9}, {%0,%1,%2,%3};"
               : "+f"(c[0]), "+f"(c[1]), "+f"(c[2]), "+f"(c[3]) : "r"(a0), "r"(a1), "r"(a2), "r"(a3), "r"(b0), "r"(b1));
}
__device__ __forceinline__ void mma_bf16_z(float (&c)[4], uint32_t a0, uint32_t a1, uint32_t a2, uint32_t a3, uint32_t b0, uint32_t b1) {
  asm volatile("mma.sync.aligned.m16n8k16.row.col.f32.bf16.bf16.f32 {%0,%1,%2,%3}, {%4,%5,%6,%7}, {%8,%9}, {%10,%10,%10,%10};"
               : "=f"(c[0]), "=f"(c[1]), "=f"(c[2]), "=f"(c[3]) : "r"(a0), "r"(a1), "r"(a2), "r"(a3), "r"(b0), "r"(b1), "f"(0.f));
}
__device__ __forceinline__ uint32_t movm_t(uint32_t v) {
  uint32_t r;
  asm volatile("movmatrix.sync.aligned.m8n8.trans.b16 %0, %1;" : "=r"(r) : "r"(v));
  return r;
}
__device__ __forceinline__ uint32_t pack_bf16(float lo, float hi) {
  uint32_t r;
  asm("cvt.rn.bf16x2.f32 %0, %1, %2;" : "=r"(r) : "f"(hi), "f"(lo));
  return r;
}
__device__ __forceinline__ float bf_lo(uint32_t v) { return __uint_as_float(v << 16); }
__device__ __forceinline__ float bf_hi(uint32_t v) { return __uint_as_float(v & 0xFFFF0000u); }
__device__ __forceinline__ void split3(float x, uint32_t& h, uint32_t& m, uint32_t& l) {
  h = pack_bf16(x, 0.f); x -= bf_lo(h);
  m = pack_bf16(x, 0.f); x -= bf_lo(m);
  l = pack_bf16(x, 0.f);
}
__device__ __forceinline__ float ex2(float x) { float r; asm("ex2.approx.ftz.f32 %0, %1;" : "=f"(r) : "f"(x)); return r; }
__device__ __forceinline__ float rcp_fast(float x) { float r; asm("rcp.approx.ftz.f32 %0, %1;" : "=f"(r) : "f"(x)); return r; }
__device__ __forceinline__ void red_v4(float* p, float a, float b, float c, float d) {
  asm volatile("red.global.add.v4.f32 [%0], {%1, %2, %3, %4};" :: "l"(p), "f"(a), "f"(b), "f"(c), "f"(d) : "memory");
}
__device__ __forceinline__ uint4 ld_ll(const uint4* p) {
  uint4 v;
  asm volatile("{\n.reg .b64 a, b;\nld.relaxed.gpu.global.v2.b64 {a, b}, [%4];\nmov.b64 {%0, %1}, a;\nmov.b64 {%2, %3}, b;\n}\n"
               : "=r"(v.x), "=r"(v.y), "=r"(v.z), "=r"(v.w) : "l"(p) : "memory");
  return v;
}
__device__ __forceinline__ void st_b64(uint2* p, uint32_t a, uint32_t b) {
  asm volatile("{\n.reg .b64 v;\nmov.b64 v, {%1, %2};\nst.relaxed.gpu.global.b64 [%0], v;\n}\n" :: "l"(p), "r"(a), "r"(b) : "memory");
}
__device__ __forceinline__ void st_b128(uint4* p, uint32_t a, uint32_t b, uint32_t c, uint32_t d) {
  asm volatile("{\n.reg .b128 v;\nmov.b128 v, {%1, %2, %3, %4};\nst.relaxed.gpu.global.b128 [%0], v;\n}\n" :: "l"(p), "r"(a), "r"(b), "r"(c), "r"(d) : "memory");
}
__device__ __forceinline__ uint4 ld_b128(const uint4* p) {
  uint4 v;
  asm volatile("{\n.reg .b128 v;\nld.relaxed.gpu.global.b128 v, [%4];\nmov.b128 {%0, %1, %2, %3}, v;\n}\n" : "=r"(v.x), "=r"(v.y), "=r"(v.z), "=r"(v.w) : "l"(p) : "memory");
  return v;
}

constexpr float LOG2E = 1.4426950408889634f;

struct Params {
  const __nv_bfloat16* x0;
  const __nv_bfloat16* wA_qkv;
  const __nv_bfloat16* wA_o;
  const __nv_bfloat16* wB_qkv;
  const __nv_bfloat16* wB_phi;
  const __nv_bfloat16* wB_o;
  __nv_bfloat16* out;
};

#define ACC_DEF(d, n) _Pragma("unroll") for (int i_ = 0; i_ < (n); i_++) asm volatile("" : "=f"(d[i_]))
#define ACC_FENCE(d, n) _Pragma("unroll") for (int i_ = 0; i_ < (n); i_++) asm volatile("" : "+f"(d[i_]) :: "memory")
#define PIN(a, n) _Pragma("unroll") for (int i_ = 0; i_ < (n); i_++) asm volatile("" : "+f"((a)[i_]))
#define PINU(a, n) _Pragma("unroll") for (int i_ = 0; i_ < (n); i_++) asm volatile("" : "+r"((a)[i_]))

#define V_ADDR(p0) uint32_t va_[2] = {(p0) + (srowoff >> 1) + (lhi ^ lsw2), (p0) + (srowoff >> 1) + ((32 + lhi) ^ lsw2)}
#define STAGE_V(acc) { \
    _Pragma("unroll") for (int j_ = 0; j_ < 4; j_++) { \
      const float* a_ = (acc) + j_ * 8; \
      stsm_x4(va_[j_ & 1] + (j_ >> 1) * 8192, \
              pack_bf16(rs0 * a_[0], rs0 * a_[1]), pack_bf16(rs1 * a_[2], rs1 * a_[3]), pack_bf16(rs0 * a_[4], rs0 * a_[5]), pack_bf16(rs1 * a_[6], rs1 * a_[7])); } }
#define FRAG(dst, acc, TR, grp) { \
    _Pragma("unroll") for (int i_ = 0; i_ < 16; i_++) { \
      const float r_ = (i_ & 1) ? rs1 : rs0; \
      const uint32_t w_ = pack_bf16(r_ * (acc)[2 * i_], r_ * (acc)[2 * i_ + 1]); \
      if (TR) (dst)[i_] = movm_t(w_); else (dst)[(i_ & 12) + (i_ & 1) * 2 + ((i_ >> 1) & 1)] = w_; } \
    if (warp == 7 && mm < 15) { \
      _Pragma("unroll") for (int j_ = 0; j_ < 4; j_++) \
        st_b128(g_halo + (size_t)(mm * 8 + jj) * 512 + ((grp) * 4 + j_) * 32 + lane, ((dst)[j_ * 4] & ~1u) | H_BIT(l), (dst)[j_ * 4 + 1], (dst)[j_ * 4 + 2], (dst)[j_ * 4 + 3]); } \
    PINU(dst, 16); }
#define FRAG_PUT(src, slot) if (warp < 7) { _Pragma("unroll") for (int j_ = 0; j_ < 4; j_++) \
      sts128(sbase + (slot) * SLOT + 2048 + warp * 2048 + j_ * 512 + lane * 16, (src)[j_ * 4], (src)[j_ * 4 + 1], (src)[j_ * 4 + 2], (src)[j_ * 4 + 3]); }
#define FRAG_GET(dst, slot) { _Pragma("unroll") for (int j_ = 0; j_ < 4; j_++) \
      asm volatile("ld.shared.v4.u32 {%0, %1, %2, %3}, [%4];" : "=r"((dst)[j_ * 4]), "=r"((dst)[j_ * 4 + 1]), "=r"((dst)[j_ * 4 + 2]), "=r"((dst)[j_ * 4 + 3]) \
                   : "r"(sbase + (slot) * SLOT + warp * 2048 + j_ * 512 + lane * 16) : "memory"); }
#define RW(j) (((j) >> 1) * 4 + ((j) & 1))
template <int POS> __device__ __forceinline__ float exps16_(float* o, const float* p) {
  float s[4];
#pragma unroll
  for (int j = 0; j < 16; j++) { o[j] = ex2(POS ? p[RW(j)] : -p[RW(j)]); if (j < 4) s[j] = o[j]; else s[j & 3] += o[j]; }
  const float r = (s[0] + s[1]) + (s[2] + s[3]);
  return r + __shfl_xor_sync(0xffffffffu, r, 1);
}
template <int POS> __device__ __forceinline__ void exps16_fix(float* o, const float* p, float& sum) {
  if (__builtin_expect(__any_sync(0xffffffffu, !(sum > SUMLO && sum < SUMHI)), 0)) {
    float m = p[0], q[32];
#pragma unroll
    for (int j = 1; j < 16; j++) m = POS ? fmaxf(m, p[RW(j)]) : fminf(m, p[RW(j)]);
    const float x = __shfl_xor_sync(0xffffffffu, m, 1);
    m = POS ? fmaxf(m, x) : fminf(m, x);
#pragma unroll
    for (int j = 0; j < 16; j++) q[RW(j)] = p[RW(j)] - m;
    sum = exps16_<POS>(o, q);
  }
}
__device__ __forceinline__ void store16(const float* e, float sum, uint32_t dst, uint32_t dsw, int c0) {
  const float inv = rcp_fast(sum);
#pragma unroll
  for (int j = 0; j < 2; j++)
    sts128(dst + (((c0 + j) << 4) ^ dsw), pack_bf16(e[j * 8] * inv, e[j * 8 + 1] * inv), pack_bf16(e[j * 8 + 2] * inv, e[j * 8 + 3] * inv),
           pack_bf16(e[j * 8 + 4] * inv, e[j * 8 + 5] * inv), pack_bf16(e[j * 8 + 6] * inv, e[j * 8 + 7] * inv));
}
template <int POS> __device__ __forceinline__ void expp16(uint32_t* o, float* p, bool big) {
  if (__builtin_expect(big, 0)) {
#pragma unroll
    for (int r = 0; r < 4; r += 2) {
      float m = p[r];
#pragma unroll
      for (int j = 1; j < 8; j++) m = POS ? fmaxf(m, p[r + RW(j)]) : fminf(m, p[r + RW(j)]);
#pragma unroll
      for (int s = 1; s <= 2; s <<= 1) { const float x = __shfl_xor_sync(0xffffffffu, m, s); m = POS ? fmaxf(m, x) : fminf(m, x); }
#pragma unroll
      for (int j = 0; j < 8; j++) p[r + RW(j)] -= m;
    }
  }
#pragma unroll
  for (int j = 0; j < 8; j++) o[j] = pack_bf16(ex2(POS ? p[2 * j] : -p[2 * j]), ex2(POS ? p[2 * j + 1] : -p[2 * j + 1]));
}
__device__ __forceinline__ void scale32(float* o, const float* p, float c0, float c1) {
#pragma unroll
  for (int i = 0; i < 32; i++) asm volatile("mul.f32 %0, %1, %2;" : "=f"(o[i]) : "f"(p[i]), "f"((i & 2) ? c1 : c0));
}
__device__ __forceinline__ bool any_big(const float* p) {
  float m[4];
#pragma unroll
  for (int i = 0; i < 32; i++) m[i & 3] = i < 4 ? fabsf(p[i]) : fmaxf(m[i & 3], fabsf(p[i]));
  return __any_sync(0xffffffffu, !(fmaxf(fmaxf(m[0], m[1]), fmaxf(m[2], m[3])) < BIGLIM));
}
#define SCHED_FENCE() asm volatile("pmevent 0;" ::: "memory")

__global__ void __cluster_dims__(2, 1, 1) __launch_bounds__(384, 1)
mega_kernel(const __grid_constant__ CUtensorMap tm_x0, const __grid_constant__ CUtensorMap tm_xo, const __grid_constant__ CUtensorMap tm_os,
            const __grid_constant__ CUtensorMap tm_o, const __grid_constant__ CUtensorMap tm_wf,
            const __grid_constant__ CUtensorMap tm_wqA, const __grid_constant__ CUtensorMap tm_wqB,
            const __grid_constant__ CUtensorMap tm_woA, const __grid_constant__ CUtensorMap tm_woB,
            const __grid_constant__ CUtensorMap tm_phi, const Params prm) {
  extern __shared__ __align__(1024) uint8_t smem_raw[];
  const uint32_t sbase = smem_u32(smem_raw);
  const uint32_t bar_full = sbase + OFF_BAR;
  const uint32_t bar_done = bar_full + 384;
  const uint32_t bar_stat = bar_full + 768, bar_stat2 = bar_full + 776, bar_epi = bar_full + 784, bar_phi = bar_full + 936  , bar_halo = bar_full + 904  ;
  const uint32_t bar_xr = bar_full + 800, bar_lx = bar_full + 808, bar_stg = bar_full + 832;
  const uint32_t bar_chk = bar_full + 848;

  const int warp = __shfl_sync(0xffffffffu, threadIdx.x >> 5, 0), lane = threadIdx.x & 31;
  uint32_t rank;
  asm volatile("mov.u32 %0, %%cluster_ctarank;" : "=r"(rank));
  const int aux = (int)blockIdx.x - NMAIN, tp = (int)(blockIdx.x >> 1) - 4;
  const int gp = tp < 0 ? 0 : (tp < 32 ? tp & 7 : 1 + (tp - 32) % 7), me = tp < 0 ? tp + 8 : (tp < 32 ? tp >> 3 : 4 + (tp - 32) / 7);
  const int jj = me, cc = gp;
  const int cta = aux >= 0 ? -1 : (cc * 8 + jj) * 2 + (int)rank;
  const int mm = cc * 2 + (int)rank;

#define LOAD_EPOCH() const unsigned epoch = ld_relaxed(&g_flags.epoch.v), ep1 = epoch + 1; (void)epoch
  int budget = 1 << 22;

  if (cta >= 0) {
    if (warp >= 8 && warp < 8 + EARLY && elect_one()) {
      const int u = warp - 8;
      const uint32_t fb = bar_full + u * 8;
      mbar_init(fb, 1);
      asm volatile("fence.mbarrier_init.release.cluster;" ::: "memory");
      fence_proxy_async_smem();
      mbar_expect_tx(fb, u < 2 ? QST + SLOT : QST);
      if (u < 2) tma_load_2d(sbase + OFF_S + u * SLOT, &tm_x0, fb, jj * 128 + u * 64, mm * 128);
#pragma unroll
      for (int i = 0; i < 6; i++) tma_load_2d(sbase + u * QST + i * 4096, &tm_wqA, fb, jj * 128 + (u >> 1) * 64 + (i >> 1) * 1024, jj * 128 + (u & 1) * 64 + (i & 1) * 32);
      if (u == 0) PROFT(472);
    }
    __syncwarp();
    {
      const int tx = threadIdx.x;
      const __nv_bfloat16* pf = (tx < 128) ? prm.x0 + (size_t)(mm * 128 + tx) * D_MODEL + jj * 128
                                           : prm.wA_qkv + (size_t)(jj * 128 + (tx & 63)) * 3072 + ((tx - 128) >> 6) * 1024 + jj * 128 + rank * 64;
      if (tx < 320) { if (PF0) asm volatile("prefetch.global.L2 [%0];" :: "l"(pf)); }
      else if (tx == 320) prefetch_tmap(&tm_x0);
      else if (tx == 352) prefetch_tmap(&tm_wqA);
      else if (tx == 383) asm volatile("prefetch.global.L2 [%0];" :: "l"(&g_flags.epoch.v));
    }
    if (elect_one()) {
#pragma unroll
      for (int i = 0; i < 4; i++) {
        const int u = warp * 4 + i;
        if (u >= EARLY) mbar_init(bar_full + u * 8, ((u >= 4 && u < 11) || (u > 32 && u != 40)) ? 2 : 1); mbar_init(bar_done + u * 8, 16);
      }
      mbar_init(bar_stat + warp * 16, 0x111111181182ull >> (4 * warp) & 15);
      mbar_init(bar_stat + warp * 16 + 8, 0x111111121811ull >> (4 * warp) & 15);
      mbar_init(bar_chk + 112 + (warp & 7) * 8, 1);
      asm volatile("fence.mbarrier_init.release.cluster;" ::: "memory");
    }
    __syncthreads();
    asm volatile("barrier.cluster.arrive.relaxed.aligned;" ::: "memory");
  }

  if (cta < 0) {
    LOAD_EPOCH();
    const uint32_t buf = sbase + warp * SLOT, bar = sbase + OFF_BAR + warp * 16;
    const uint32_t lsw = (lane & 7) << 4, lhi = (lane >> 4) << 4, lrow = (lane & 15) * 128;
    const bool el = elect_one();
    if (el) {
      mbar_init(bar, 1); mbar_init(bar + 8, 1);
      asm volatile("fence.mbarrier_init.release.cluster;" ::: "memory");
    }
#pragma unroll 1
    for (int rd = 0; rd < (NLAYERS > 1 ? 5 : 2); rd++) {
      if (rd >= 2 && warp >= 8) break;
      const int tk = rd < 2 ? aux * 12 + warp : aux * 8 + warp;
      const int half = tk & 1;
      const int blk = rd < 2 ? (tk >> 1) * 2 + rd : (4 - rd) * 16 + (tk >> 1);
      const CUtensorMap* tm = rd < 2 ? &tm_wqA : (rd == 2 ? &tm_wqB : &tm_wf);
      const int j0 = (blk & 15) >> 1;
#define AUX_LOAD(n) { const uint32_t d_ = buf + ((n) & 1) * 8192, b_ = bar + ((n) & 1) * 8; const int r_ = kslice(j0, 2 * (n) + half) * 64; \
        mbar_expect_tx(b_, 8192); tma_load_2d(d_, tm, b_, blk * 64, r_); tma_load_2d(d_ + 4096, tm, b_, blk * 64, r_ + 32); }
      if (el) {
        if (rd == 3) { wait_flag(&g_flags.wfready[j0].v, ep1 * 16); fence_proxy_async_global(); }
        AUX_LOAD(0); AUX_LOAD(1);
      }
      __syncwarp();
      float cs[8][4];
#pragma unroll
      for (int i = 0; i < 8; i++) cs[i][0] = cs[i][1] = cs[i][2] = cs[i][3] = 0.f;
#pragma unroll 1
      for (int n = 0; n < 8; n++) {
        const uint32_t tb = buf + (n & 1) * 8192 + lrow;
        mbar_wait(bar + (n & 1) * 8, (n >> 1) & 1);
#pragma unroll
        for (int i = 0; i < 16; i++) {
          uint32_t b0, b1, b2, b3;
          ldsm_x4_t(tb + (i >> 2) * 2048 + (((i & 3) * 32 + lhi) ^ lsw), b0, b1, b2, b3);
          mma_bf16(cs[2 * (i & 3)], 0x3F803F80u, 0x3F803F80u, 0x3F803F80u, 0x3F803F80u, b0, b1);
          mma_bf16(cs[2 * (i & 3) + 1], 0x3F803F80u, 0x3F803F80u, 0x3F803F80u, 0x3F803F80u, b2, b3);
        }
        __syncwarp();
        if (el && n < 6) AUX_LOAD(n + 2);
        __syncwarp();
      }
      if (lane < 4) {
#pragma unroll
        for (int i = 0; i < 8; i++) st_b64(&g_colsum[rd >= 2][blk * 32 + i * 4 + lane][half], __float_as_uint(cs[i][0]), (__float_as_uint(cs[i][1]) & ~3u) | (ep1 & 3));
      }
      __syncwarp();
    }
  } else if (warp >= 8) {
    asm volatile("setmaxnreg.dec.sync.aligned.u32 40;");
    if (warp == 8) {
      const bool el = elect_one();
      cluster_wait();
      if (el) {
#pragma unroll 1
        for (int l = 0; l < NLAYERS; l++) {
          const uint32_t par = l & 1;
          const CUtensorMap* tqk = par ? &tm_wf : &tm_wqA;
          const CUtensorMap* tv = par ? &tm_wqB : &tm_wqA;
          const CUtensorMap* two = par ? &tm_woB : &tm_woA;
          if (l == 1) { LOAD_EPOCH(); wait_flag(&g_flags.wfready[jj].v, ep1 * 16); fence_proxy_async_global(); }
#pragma unroll 1
          for (int u = l ? 0 : EARLY; u < 32; u++) {
            if (u >= 4) mbar_wait_sl(bar_done + (u - 4) * 8, par);
            else if (l) mbar_wait_sl(bar_done + (43 + u + (u >> 1)) * 8, par ^ 1);
            else if (u == 1) __nanosleep(STAG1);
            else if (u == 2 && !W23) mbar_wait_sl(bar_full, 0);
            const uint32_t fb = bar_full + u * 8;
            const bool res = u < 4 ? (l || u >= 2) : (u < 11 || (u >= 18 && u < 22));
            mbar_expect_tx(fb, res ? QST : QST + SLOT);
            const int row = kslice(jj, u < 4 ? u & 1 : (u < 18 ? u - 2 : (u < 22 ? u - 6 : u - 20))) * 64 + (int)rank * 32;
            const int ps = u < 4 ? u >> 1 : (u >= 18), col = jj * 128 + ps * 64;
            const int c0 = par ? jj * 128 + (ps ? 0 : 1024) : col;
            const uint32_t dst = sbase + (u & 3) * QST + rank * 4096;
            tma_load_2d_mc(dst, tqk, fb, c0, row);
            tma_load_2d_mc(dst + 8192, tqk, fb, c0 + (par ? 64 : 1024), row);
            tma_load_2d_mc(dst + 16384, tv, fb, col + 2048, row);
            if (l == PRL && u >= PRU && u < PRU + 4) PROFT(473 + u - PRU);
          }
#pragma unroll 1
          for (int s = 0; s < 16; s++) {
            if (s < 5) { if (s != 2 && s != 4) mbar_wait_sl(bar_done + (28 + s) * 8, par); }
            else if (s != 14) mbar_wait_sl(bar_done + (27 + s - (s == 15)) * 8, par);
            const uint32_t fb = bar_full + (32 + s) * 8;
            mbar_expect_tx(fb, SLOT);
            tma_load_2d_mc(sbase + rank * 8192 + (uint32_t)((WO_BSLOT >> (4 * s)) & 15) * SLOT, two, fb, jj * 128 + (int)rank * 64, wslice(jj, s) * 64);
            const int ts = s + par;
            if (s >= 5 && ts < 8) {
              mbar_expect_tx(bar_chk - 8 + ts * 8, SLOT);
              tma_load_2d(sbase + (uint32_t)((WO_ASLOT(par) >> (4 * ts)) & 15) * SLOT, &tm_o, bar_chk - 8 + ts * 8, wslice(jj, ts) * 64, mm * 128);
            }
          }
        }
      }
      __syncwarp();
    } else if (warp == 9) {
      const bool el = elect_one();
      if (el) {
        if (!EARLY) { PROFT(472); tma_load_2d(sbase + OFF_S, &tm_x0, bar_full, jj * 128, mm * 128); }
        if (EARLY < 2) { __nanosleep(STAG1); tma_load_2d(sbase + OFF_S + SLOT, &tm_x0, bar_full + 8, jj * 128 + 64, mm * 128); }
      }
      __syncwarp();
      LOAD_EPOCH();
#pragma unroll 1
      for (int lp = 0; lp < 4 * NLAYERS; lp++) {
        const int l = lp >> 2, ph = lp & 3;
        if (ph == 3) continue;
        const uint32_t par = l & 1;
        const unsigned* pp = reinterpret_cast<const unsigned*>(g_obuf + (ph >> 1) * 64 + (size_t)(mm * 128 + (ph ? 0 : S_LEN) + (lane & 7) * 16 + (jj & 1) * 8) * D_MODEL +
                                                               (jj >> 1) * 16 + srcb(jj, lane >> 3) * 128);
        const CUtensorMap* tm = lp ? &tm_o : &tm_x0;
        const int row = mm * 128 + ((ph || !l) ? 0 : S_LEN);
        const uint32_t bit = ph ? O_BIT(l) : X_BIT(l - 1);
        const uint32_t slots = ph ? (uint32_t)(WO_ASLOT(par) >> (ph * 32 - 28)) : 0x8769876u;
        const unsigned long long fr = ph == 0 ? XPACE : ph == 1 ? (par ? 0x353535351Full : 0x35351F1Eull) : (par ? 0x27262524232232ull : 0x27262524233232ull);
        uint32_t no = (lp == 0 || (lp & 7) == 1) ? 0 : ~0u, v0 = 0, v1 = 0;
        if (lp || !AX) mbar_wait_sl(ph ? bar_done + ((uint32_t)fr & 63) * 8 : (l ? bar_done + 47 * 8 : bar_full), ph ? par : (l ? par ^ 1 : 0));
        if (el && ph) PROFT(324 + l * 16 + ph);
        __syncwarp();
        if (no) { v0 = ld_relaxed(pp); __nanosleep(POLLGAP); v1 = ld_relaxed(pp); }
#pragma unroll 1
        for (int i = 0; i < (ph == 1 ? 4 + par : 7); i++, no >>= 8) {
#pragma unroll 1
          for (int it = 0; (no & 0xFF) && it < (1 << 18); it++) {
            no &= __ballot_sync(0xffffffffu, (v0 ^ bit) & 1) >> (8 * i);
            if (no) v0 = ld_relaxed(pp);
            if (!(no & 0xFF)) break;
            no &= __ballot_sync(0xffffffffu, (v1 ^ bit) & 1) >> (8 * i);
            if (no) v1 = ld_relaxed(pp);
          }
          if (ph || i >= XP0) mbar_wait_sl(bar_done + ((uint32_t)(fr >> (8 * i)) & 63) * 8, par);
          if (el) {
            if (i == 0) PROFT(320 + l * 16 + ph);
            const uint32_t cb = bar_chk + (ph >> 1) * 112 + i * 8;
            mbar_expect_tx(cb, SLOT);
            tma_load_2d(sbase + ((slots >> (4 * i)) & 15) * SLOT, tm, cb, srcb(jj, i) * 128 + (ph >> 1) * 64, row);
          }
          __syncwarp();
        }
        if (ph == 0 && el) {
          if (l) { wait_flag(&g_flags.xready[l][mm].v, ep1 * 8); fence_proxy_async_global(); }
#pragma unroll 1
          for (int u = 11; u < 34; u++) {
            if (u == 18) u = 22;
            mbar_wait_sl(bar_done + (u - 4) * 8, par);
            if (u == 32) mbar_expect_tx(bar_xr, 2 * SLOT);
            tma_load_2d(sbase + OFF_RA + (u & 3) * SLOT, tm, u < 32 ? bar_full + u * 8 : bar_xr, kslice(jj, u < 18 ? u - 2 : (u < 32 ? u - 20 : u - 32)) * 64, row);
          }
        }
        __syncwarp();
      }
      if (el && atomicAdd(&g_flags.done.v, 1) == ep1 * NMAIN - 1) asm volatile("st.relaxed.gpu.global.u32 [%0], %1;" :: "l"(&g_flags.epoch.v), "r"(ep1) : "memory");
      __syncwarp();
      cluster_wait();
    } else {
      const int hw = warp - 10;
      LOAD_EPOCH();
      const bool el = elect_one();
      cluster_wait();
      if (hw == 0) {
        mbar_wait_sl(bar_full + 8, 0);
        if (lane < 7) prefetch_tmap(lane == 0 ? &tm_os : lane == 1 ? &tm_o : lane == 2 ? &tm_wf : lane == 3 ? &tm_wqB : lane == 4 ? &tm_woA : lane == 5 ? &tm_woB : &tm_phi);
#pragma unroll 1
        for (int i = 0; i < (NLAYERS > 1 ? 9 : 0); i++) {
          if (i == 0 || i == 5) mbar_wait_sl(bar_done + (i >> 1) * 12, 0);
          if (el) {
            if (i == 0) { mbar_expect_tx(bar_phi, 2 * SLOT + 8192); tma_load_2d(sbase + OFF_PHI, &tm_phi, bar_phi, 0, jj * 128); }
            else tma_load_2d(sbase + (i > 4 ? 10 : 12) * SLOT - 4096 + i * 4096, &tm_wqB, bar_phi, (i > 4 ? 896 : 0) + jj * 128 + ((i - 1) >> 1) * 64, mm * 64 + (~i & 1) * 32);
          }
          __syncwarp();
          __nanosleep(PFGAP);
        }
      } else {
#pragma unroll 1
        for (int b = 0; b < 2; b++) {
          float4* z = reinterpret_cast<float4*>(g_kv[b] + (jj * 4) * KVH + mm * (4 * KVH / 16)) + lane;
#pragma unroll
          for (int i = 0; i < 6; i++) z[i * 32] = make_float4(0.f, 0.f, 0.f, 0.f);
        }
#pragma unroll 1
        for (int i = 0; i < 16; i++) {
          const int b = i >> 2;
          const uint32_t v = (b == 0 ? O_BIT(0) : b == 1 ? X_BIT(0) : H_BIT(0)) + 1;
          uint4* p = b < 2 ? reinterpret_cast<uint4*>(g_obuf + (size_t)(b * S_LEN + mm * 128 + (i & 3) * 32 + (lane >> 3) * 8) * D_MODEL + jj * 128 + (b ? 0 : 64)) + (lane & 7)
                           : g_halo + (size_t)(mm * 8 + jj) * 512 + i * 32 + lane;
          *p = make_uint4(v, v, v, v);
        }
        fence_proxy_async_global();
      }
      __syncwarp();
      uint32_t chkp = 0;
#pragma unroll 1
      for (int lp = 0; lp < 4 * NLAYERS; lp++) {
        const int l = lp >> 2, ph = (lp & 3) == 2 ? 2 - hw : (lp & 3);
        const uint32_t par = l & 1;
        int lane; asm volatile("mov.u32 %0, %%laneid;" : "=r"(lane));
        if ((lp & 3) == 2 || (hw && ph == 0)) {
          const uint32_t bit = ph ? O_BIT(l) : X_BIT(l - 1);
          uint32_t slots = ph ? (uint32_t)(WO_ASLOT(par) >> (ph * 32 - 28)) : 0x8769876u;
          const uint32_t a0 = sbase + (lane & 7) * 132 + (lane >> 3) * 32;
#pragma unroll 1
          for (int c = 0; c < 7; c++, slots >>= 4) {
            const uint32_t cb = bar_chk + 112 - hw * 112 + c * 8;
#pragma unroll 1
            for (int it = 0; it < (1 << 12); it++) {
              mbar_wait_sl(cb, (chkp >> c) & 1);
              chkp ^= 1u << c;
              if (el && c == 0) PROFT(ph == 1 ? 480 + l * 2 : 488 + l * 2 + (ph >> 1));
              if (lp == 0) break;
              uint32_t bad;
              asm volatile("{\n.reg .b32 w<16>;\n"
                           "ld.shared.u32 w0, [%1 + 0];\n"
                           "ld.shared.u32 w1, [%1 + 1024];\n"
                           "ld.shared.u32 w2, [%1 + 2048];\n"
                           "ld.shared.u32 w3, [%1 + 3072];\n"
                           "ld.shared.u32 w4, [%1 + 4096];\n"
                           "ld.shared.u32 w5, [%1 + 5120];\n"
                           "ld.shared.u32 w6, [%1 + 6144];\n"
                           "ld.shared.u32 w7, [%1 + 7168];\n"
                           "ld.shared.u32 w8, [%1 + 8192];\n"
                           "ld.shared.u32 w9, [%1 + 9216];\n"
                           "ld.shared.u32 w10, [%1 + 10240];\n"
                           "ld.shared.u32 w11, [%1 + 11264];\n"
                           "ld.shared.u32 w12, [%1 + 12288];\n"
                           "ld.shared.u32 w13, [%1 + 13312];\n"
                           "ld.shared.u32 w14, [%1 + 14336];\n"
                           "ld.shared.u32 w15, [%1 + 15360];\n"
                           "lop3.b32 w0, w0, w1, %2, 0x7E;\n"
                           "lop3.b32 w2, w2, w3, %2, 0x7E;\n"
                           "lop3.b32 w4, w4, w5, %2, 0x7E;\n"
                           "lop3.b32 w6, w6, w7, %2, 0x7E;\n"
                           "lop3.b32 w8, w8, w9, %2, 0x7E;\n"
                           "lop3.b32 w10, w10, w11, %2, 0x7E;\n"
                           "lop3.b32 w12, w12, w13, %2, 0x7E;\n"
                           "lop3.b32 w14, w14, w15, %2, 0x7E;\n"
                           "lop3.b32 w0, w0, w2, w4, 0xFE;\nlop3.b32 w6, w6, w8, w10, 0xFE;\nlop3.b32 w0, w0, w12, w14, 0xFE;\nlop3.b32 %0, w0, w6, 1, 0xA8;\n}\n"
                           : "=r"(bad) : "r"(a0 + (slots & 15) * SLOT), "r"(bit) : "memory");
              if (__all_sync(0xffffffffu, bad == 0)) break;
              if (el) {
                fence_proxy_async_smem();
                mbar_expect_tx(cb, SLOT);
                tma_load_2d(sbase + (slots & 15) * SLOT, &tm_o, cb, srcb(jj, c) * 128 + (ph >> 1) * 64, mm * 128 + (ph ? 0 : S_LEN));
                RETRY_COUNT();
              }
              __syncwarp();
            }
            if (el) { mbar_arrive_local(bar_full + (c + (ph ? 25 + ph * 8 : 4)) * 8); if (lp == PRL * 4 && c == 0) PROFT(477); }
            __syncwarp();
          }
          if (ph) continue;
#pragma unroll 1
          for (int hp = 0; hp < 2; hp++) {
            const uint4* src = reinterpret_cast<const uint4*>(g_colsum[par][jj * 64 + hp * 32 + lane]);
            uint32_t bad;
            int it = 0;
            float c[6];
            do {
              bad = 0;
#pragma unroll
              for (int p = 0; p < 3; p++) {
                const uint4 v = ld_ll(src + ((par && p < 2) ? (hp ? -32 : 512) + p * 32 : p * 512));
                bad |= (v.y ^ ep1) | (v.w ^ ep1);
                c[2 * p] = __uint_as_float(v.x) + __uint_as_float(v.z); c[2 * p + 1] = __uint_as_float(v.y) + __uint_as_float(v.w);
              }
              bad &= 3;
              if (bad) __nanosleep(300);
            } while (bad && ++it < (1 << 16));
#pragma unroll
            for (int p = 0; p < 6; p++) {
              uint32_t h, m, lo;
              split3(c[p], h, m, lo);
              sts128(sbase + OFF_LNB + hp * 4096 + (p >> 1) * 1024 + lane * 32 + (p & 1) * 16, h | (m << 16), h | (lo << 16), h | (m << 16), lo | (m << 16));
            }
            fence_proxy_async_smem();
            __syncwarp();
            if (el) { mbar_arrive_local(hp ? bar_stat2 : bar_stat); if (hp == 0) PROFT(324 + l * 16); }
            __syncwarp();
          }
          continue;
        } else if (ph == 0) {
          mbar_wait_sl(bar_done + 24, par);
          const uint4* sp = reinterpret_cast<const uint4*>(g_stats + (size_t)(mm * 128) * 8) + lane;
#pragma unroll 1
          for (int hf = 0; hf < 4; hf++) {
            uint4 v[4];
            uint32_t bad;
            int it = 0;
            do {
              bad = 0;
#pragma unroll
              for (int i = 0; i < 4; i++) { v[i] = ld_ll(sp + (hf * 4 + i) * 32); bad |= (v[i].y ^ STAT_TAG(l)) | (v[i].w ^ STAT_TAG(l)); }
              bad &= 3;
              if (bad) __nanosleep(200);
            } while (bad && ++it < (1 << 16));
            __syncwarp();
            float mean = 0.f, m2 = 0.f;
#pragma unroll
            for (int i = 0; i < 4; i++) {
              float a = __uint_as_float(v[i].x) + __uint_as_float(v[i].z);
              a += __shfl_xor_sync(0xffffffffu, a, 1); a += __shfl_xor_sync(0xffffffffu, a, 2);
              a *= 0.125f;
              const float e0 = __uint_as_float(v[i].x) - a, e1 = __uint_as_float(v[i].z) - a;
              float q = fmaf(fmaf(e0, e0, e1 * e1), 128.f, __uint_as_float(v[i].y) + __uint_as_float(v[i].w));
              q += __shfl_xor_sync(0xffffffffu, q, 1); q += __shfl_xor_sync(0xffffffffu, q, 2);
              if ((lane & 3) == i) { mean = a; m2 = q; }
            }
            const uint32_t row = hf * 32 + (lane & 3) * 8 + (lane >> 2);
            uint32_t h, m, lo;
            split3(-0.5f * mean, h, m, lo);
            sts128(sbase + OFF_LNA + row * 16, h | (h << 16), m | (h << 16), lo | (m << 16), m | (lo << 16));
            sts32f(sbase + OFF_ST + row * 4, rsqrtf(m2 * (1.f / 1024.f) + 1e-5f));
          }
          fence_proxy_async_smem();
          __syncwarp();
          if (el) { mbar_arrive_local(bar_stat); PROFT(323 + l * 16); }
          __syncwarp();
#pragma unroll 1
          for (int i = 0; i < 8 - 4 * l; i++) {
            asm volatile("prefetch.global.L2 [%0];" :: "l"(i < 4 ? (l ? prm.wB_o : prm.wA_o) + (size_t)cta * 8192 + i * 2048 + lane * 64
                                                                 : prm.wB_qkv + (size_t)(cta * 8 + (i - 4) * 2 + (lane >> 4)) * 3072 + 2048 + (lane & 15) * 64));
            __nanosleep(PFGAP);
          }
          continue;
        }
        if (ph == 1) {
          if (par) continue;
#pragma unroll 1
          for (int i = 0; i < 2; i++) {
            if (i && lp + hw == 1 && NLAYERS > 1) {
#pragma unroll 1
              for (int c = 0; c < 8; c++) {
                if (!(c & 3)) asm volatile("bar.sync %0, 288;" :: "r"(BAR_WF + (c >> 2)) : "memory");
                if (el) {
                  tma_store_2d(&tm_wf, sbase + 11 * SLOT + c * 4096, (c < 4 ? 1024 : -128) + jj * 128 + (c >> 1) * 64, mm * 64 + (c & 1) * 32);
                  if ((c & 3) == 3) {
                    asm volatile("cp.async.bulk.commit_group;\ncp.async.bulk.wait_group.read 0;" ::: "memory");
                    mbar_arrive_local(bar_phi + (c >> 2) * 8);
                  } else __nanosleep(WFGAP);
                }
                __syncwarp();
              }
              if (el) { bulk_commit_wait(); signal_release(&g_flags.wfready[jj].v); PROFT(335); }
              __syncwarp();
            }
            mbar_wait_sl(bar_done + (i ? HW1 : (hw ? 19 : HW0)) * 8, 0);
            if (lp + hw == 2 && NLAYERS > 1) mbar_wait_sl(bar_phi, 1);
            const uint4* src = g_halo + (size_t)(mm * 8 + jj - 8) * 512 + i * 256 + hw * 128 + lane;
            uint4 v[4];
            int it = 0;
            bool ok;
            do {
#pragma unroll
              for (int j = 0; j < 4; j++) v[j] = mm ? ld_b128(src + j * 32) : make_uint4(H_BIT(l), 0, 0, 0);
              ok = __all_sync(0xffffffffu, (((v[0].x ^ H_BIT(l)) | (v[1].x ^ H_BIT(l)) | (v[2].x ^ H_BIT(l)) | (v[3].x ^ H_BIT(l))) & 1) == 0);
            } while (!ok && ++it < (1 << 16));
#pragma unroll
            for (int j = 0; j < 4; j++) sts128(sbase + OFF_S + hw * SLOT + j * 512 + lane * 16, v[j].x, v[j].y, v[j].z, v[j].w);
            __syncwarp();
            if (el) { mbar_arrive_local(bar_halo + hw * 8); PROFT(331 + l * 16 + i * 2 + hw); }
            __syncwarp();
          }
        } else if (hw == 0 && l < NLAYERS - 1) {
          bar_sync<BAR_X1, 288>();
          if (el) {
            PROFT(328 + l * 16);
            mbar_wait_sl(bar_full + XD * 8, par ^ 1);
            tma_store_2d(&tm_o, sbase + 11 * SLOT, jj * 128 + 64, mm * 128 + S_LEN);
            bulk_commit_wait();
            signal_release(&g_flags.xready[l + 1][mm].v);
            PROFT(330 + l * 16);
          }
          __syncwarp();
        }
      }
    }
    cluster_sync();
  } else {
    asm volatile("setmaxnreg.inc.sync.aligned.u32 232;");
    LOAD_EPOCH();
    const int wg = warp >> 2;
    const int r0 = warp * 16;
    const uint32_t pK = sbase + OFF_S, pV = sbase + OFF_S + SLOT;
#define PMASKS(on, bit) const uint32_t pm0 = ((on) && t == (g & 3) && (g >> 2) == (g & 1)), pm1 = ((on) && t == (g & 3) && (g >> 2) != (g & 1)), pbit = (bit)
#define PBIT0(w) (((w) & ~pm0) | (pbit & pm0))
#define PBIT1(w) (((w) & ~pm1) | (pbit & pm1))
#define LANE_CONSTS() \
    int lane; asm volatile("mov.u32 %0, %%laneid;" : "=r"(lane)); \
    const int g = lane >> 2, t = lane & 3; \
    const uint32_t srowoff = (r0 + (lane & 15)) * 128, lsw = (lane & 7) << 4, lhi = (lane >> 4) << 4, lsw2 = (lane & 6) << 3; \
    (void)g; (void)t; (void)srowoff; (void)lsw; (void)lhi; (void)lsw2;
    uint32_t stgp = 0, peer;
    asm volatile("mapa.shared::cluster.u32 %0, %1, %2;" : "=r"(peer) : "r"(sbase), "r"(rank ^ 1));
    peer -= sbase;
    const uint32_t dA0 = (((sbase & 0x3FFFF) + wg * 8192) >> 4) | 0x10000u, dB0 = ((sbase & 0x3FFFF) >> 4) | 0x2000000u;
    cluster_wait();
#define DESC(lo, hi) ((uint64_t)(uint32_t)(lo) | ((uint64_t)(hi) << 32))
#define STG_ARRIVE() { __syncwarp(); if (elect_one()) mbar_arrive_local(bar_stg); }
#define STG_WAIT() { mbar_wait(bar_stg, stgp); stgp ^= 1; }
#define PROFS() do {} while (0)
#define REL(addr) { if (elect_one()) { mbar_arrive_local(addr); asm volatile("mbarrier.arrive.shared::cluster.b64 _, [%0];" :: "r"((addr) + peer) : "memory"); } }
#define QSTEP(ACC, DA, SC, PRE) { \
      const uint32_t da = (DA), db = dB0 + (ub & 0x18) * (QST >> 7); \
      mbar_wait(ub, par); \
      PRE; \
      wgmma_fence(); \
      wgmma4_n192<SC>(ACC, da, db); \
      wgmma_commit(); PROFS(); }
#define QREL() { wgmma_wait<1>(); REL(ub + 376); ub += 8; }
#define RA_CUR (dA0 + (OFF_RA >> 4) + (ub & 0x18) * (SLOT >> 7))
#define PUMP1() { QSTEP(S1, RA_CUR, 1, {}); QREL(); }
#define PUMP0() { PUMP1(); SCHED_FENCE(); }
#define PUMP() if (h == 0) PUMP1()
#define WSTEP() { \
      const uint32_t s4 = (ub - bar_full - 256) >> 1; \
      const uint32_t da = dA0 + (((uint32_t)(WO_ASLOT(par) >> s4) & 15) << 10), db = dB0 + (((uint32_t)(WO_BSLOT >> s4) & 15) << 10); \
      mbar_wait(ub, par); \
      wgmma_fence(); \
      wgmma4_n128<1>(S1, da, db); \
      wgmma_commit(); PROFS(); \
      wgmma_wait<1>(); \
      if (s4) REL(ub + 376); \
      ub += 8; }
#define PUMPS(n) { _Pragma("unroll 1") for (int i_ = 0; i_ < (n); i_++) PUMP1(); }
#define SITE(n) { if ((BMASK >> (n)) & 1) PUMP1(); SCHED_FENCE(); }
#define LNSTEP(ACC, hh) { wgmma_fence(); wgmma_n192<1, 0>(ACC, make_desc(sbase + OFF_LNA + wg * 1024, 0, 128) ^ (1ull << 62), make_desc(sbase + OFF_LNB + (hh) * 4096, 0, 128) ^ (1ull << 62)); }
#define WARP_STORE(tm, tile, col, row) { fence_proxy_async_smem(); __syncwarp(); \
      if (elect_one()) { tma_store_2d(tm, (tile) + r0 * 128, col, (row) + r0); asm volatile("cp.async.bulk.commit_group;" ::: "memory"); } __syncwarp(); }
#define PUBLISH_O() WARP_STORE(&tm_os, pO, jj * 128 + h * 64, mm * 128)
#define TILE_CONSTS(base, on, bit) \
      uint32_t ta[6]; \
      { PMASKS(on, bit); (void)pbit; ta[4] = pm0; ta[5] = pm1; } \
      _Pragma("unroll") for (int j = 0; j < 4; j++) ta[j] = (base) + srowoff + ((((uint32_t)j << 5) + lhi) ^ lsw); \
      PINU(ta, 6); SCHED_FENCE(); \
      const uint32_t pm0 = ta[4], pm1 = ta[5], pbit = (bit)
#define X_OUT(pc) { \
      _Pragma("unroll") for (int j = (pc) * 4; j < (pc) * 4 + 4; j++) \
        stsm_x4(ta[j & 3] + (pc) * SLOT, \
                PBIT0(pack_bf16(S1[j * 8 + 0], S1[j * 8 + 1])), PBIT0(pack_bf16(S1[j * 8 + 2], S1[j * 8 + 3])), \
                PBIT1(pack_bf16(S1[j * 8 + 4], S1[j * 8 + 5])), PBIT1(pack_bf16(S1[j * 8 + 6], S1[j * 8 + 7]))); }
#define REST_P1(SKEW) { \
      mbar_wait(bar_stat2, par); \
      LNSTEP(S1, 1); \
      _Pragma("unroll 1") while (ub < bar_full + 256) { \
        if (ub == bar_full + 256 - 8 * (SKEW) && wg == 0) bar_sync<BAR_SKEW, 256>(); \
        QSTEP(S1, RA_CUR, 1, {}); \
        if (ub == bar_full + 248 && wg == 1) bar_arrive<BAR_SKEW, 256>(); \
        QREL(); \
      } \
      mbar_wait(bar_done + (31 - (SKEW)) * 8, par);        \
      wgmma_wait<0>(); \
      ACC_FENCE(S1, 96); \
      REL(bar_done + 31 * 8); \
      PROF(13); }
#define FOLD(tile, rd) { \
          LANE_CONSTS(); \
          float d[32]; \
          ACC_DEF(d, 32); \
          mbar_wait(bar_phi, 0); \
          wgmma_fence(); \
          _Pragma("unroll") for (int i = 0; i < 2; i++) { \
            const uint64_t da = make_desc((tile) + wg * 8192 + i * 64, 16, 1024); \
            const uint64_t db = make_desc(sbase + OFF_PHI + wg * 4096 + i * 2048, 16, 512) ^ (3ull << 62); \
            wgmma_n32<0>(d + i * 16, da, db); wgmma_n32<1>(d + i * 16, da + 2, db + 64); \
          } \
          wgmma_commit(); \
          PUMP0(); \
          ACC_FENCE(d, 32); \
          bar_wg(wg); \
          _Pragma("unroll") for (int i = 0; i < 4; i++) { \
            const float* x = d + (i & 1) * 8 + (i >> 1) * 2; \
            if (rd) sts128((tile) + wg * 8192 + ((warp & 3) * 16 + (i >> 1) * 8 + g) * 128 + (((2 * t + (i & 1)) ^ g) << 4), \
                           pack_bf16(x[0], x[1]), pack_bf16(x[4], x[5]), pack_bf16(x[16], x[17]), pack_bf16(x[20], x[21])); \
            else stsm_x4((tile) + srowoff + ((((uint32_t)i << 5) + lhi) ^ lsw), pack_bf16(d[i * 8], d[i * 8 + 1]), pack_bf16(d[i * 8 + 2], d[i * 8 + 3]), \
                         pack_bf16(d[i * 8 + 4], d[i * 8 + 5]), pack_bf16(d[i * 8 + 6], d[i * 8 + 7])); \
          } \
          }
#define LOAD_X0(base) \
      _Pragma("unroll") for (int j = 0; j < 8; j++) { \
        uint32_t x0, x1, x2, x3; \
        ldsm_x4((base) + (j >> 2) * SLOT + srowoff + ((((uint32_t)(j & 3) << 5) + lhi) ^ lsw), x0, x1, x2, x3); \
        S1[j * 8 + 0] = bf_lo(x0); S1[j * 8 + 1] = bf_hi(x0); S1[j * 8 + 2] = bf_lo(x1); S1[j * 8 + 3] = bf_hi(x1); \
        S1[j * 8 + 4] = bf_lo(x2); S1[j * 8 + 5] = bf_hi(x2); S1[j * 8 + 6] = bf_lo(x3); S1[j * 8 + 7] = bf_hi(x3); \
      }
#define LOAD_X() { \
      wgmma_wait<0>(); \
      mbar_wait(bar_xr, par); \
      LOAD_X0(sbase + OFF_RA); \
      ACC_FENCE(S1, 64); \
      __syncwarp(); if (elect_one()) mbar_arrive_local(bar_lx); }

    float S1[96];
#pragma unroll
    for (int i = 0; i < 64; i++) S1[i] = 0.f;
#pragma unroll 1
    for (int l = 0; l < NLAYERS; l++) {
      const uint32_t par = l & 1;
      bar_wg(wg);
      PROF(0);
      uint32_t ub = bar_full;
      float S0[96];
      {
        LANE_CONSTS();
        ACC_DEF(S0, 96);
        QSTEP(S0, dA0 + (OFF_S >> 4), 0, {});
        ub += 8;
        PROF(1);
        if (l == 0) { mbar_wait(ub, 0); LOAD_X0(pK); }
        else { uint32_t ta[4]; for (int j = 0; j < 4; j++) ta[j] = pK + srowoff + ((((uint32_t)j << 5) + lhi) ^ lsw); PMASKS(false, 0); X_OUT(1); fence_proxy_async_smem(); }
        SCHED_FENCE();
        {
          float a0 = S1[0], a1 = S1[2], b0 = S1[1], b1 = S1[3];
#pragma unroll
          for (int i = 4; i < 64; i += 4) { a0 += S1[i]; b0 += S1[i + 1]; a1 += S1[i + 2]; b1 += S1[i + 3]; }
          a0 += b0; a1 += b1;
          a0 += __shfl_xor_sync(0xffffffffu, a0, 1); a1 += __shfl_xor_sync(0xffffffffu, a1, 1);
          a0 += __shfl_xor_sync(0xffffffffu, a0, 2); a1 += __shfl_xor_sync(0xffffffffu, a1, 2);
          a0 *= (1.f / 128.f); a1 *= (1.f / 128.f);
          asm volatile("" : "+f"(a0), "+f"(a1));
          bar_wg(wg);
          QSTEP(S0, dA0 + ((OFF_S + SLOT) >> 4), 1, wgmma_wait<0>());
          REL(ub + 376); ub += 8;
          SCHED_FENCE();
          float q0 = 0.f, q1 = 0.f;
          b0 = 0.f; b1 = 0.f;
#pragma unroll
          for (int i = 0; i < 64; i += 4) {
            const float d0 = S1[i] - a0, d1 = S1[i + 1] - a0, d2 = S1[i + 2] - a1, d3 = S1[i + 3] - a1;
            q0 = fmaf(d0, d0, q0); b0 = fmaf(d1, d1, b0); q1 = fmaf(d2, d2, q1); b1 = fmaf(d3, d3, b1);
          }
          q0 += b0; q1 += b1;
          q0 += __shfl_xor_sync(0xffffffffu, q0, 1); q1 += __shfl_xor_sync(0xffffffffu, q1, 1);
          q0 += __shfl_xor_sync(0xffffffffu, q0, 2); q1 += __shfl_xor_sync(0xffffffffu, q1, 2);
          if (t < 2) st_b64(g_stats + (size_t)(mm * 128 + r0 + g + t * 8) * 8 + jj, __float_as_uint(t ? a1 : a0), (__float_as_uint(t ? q1 : q0) & ~3u) | STAT_TAG(l));
        }
        if (l) { asm volatile("cp.async.bulk.wait_group 0;" ::: "memory"); bar_arrive<BAR_X1, 288>(); }
        ACC_DEF(S1, 96);
        QSTEP(S1, dA0 + (OFF_S >> 4), 0, {});
        QREL();
        QSTEP(S1, dA0 + ((OFF_S + SLOT) >> 4), 1, {});
        QREL();
#pragma unroll 1
        for (int i = 0; i < 14; i++) {
          QSTEP(S0, RA_CUR, 1, {});
          if (i == 0) PROF(2);
          QREL();
        }
      }
      LANE_CONSTS();
      mbar_wait(bar_stat, par);
      LNSTEP(S0, 0);
      wgmma_commit();
      const float rs0 = lds32f(sbase + OFF_ST + (r0 + g) * 4), rs1 = lds32f(sbase + OFF_ST + (r0 + g + 8) * 4);
      PUMP0();
      ACC_FENCE(S0, 96);
      PROF(3);
      if (!par) {
        constexpr uint32_t par = 0;
        uint32_t qa[16];
        uint32_t kf[32], vf[32];
#define DRAIN_A(ACC, hp, PMP) { \
          LANE_CONSTS(); \
          FRAG(kf + 16, ACC + 32, 0, (hp) * 2); \
          PMP; \
          FRAG(vf + 16, ACC + 64, 1, (hp) * 2 + 1); \
          _Pragma("unroll") for (int i_ = 0; i_ < 16; i_++) qa[i_] = pack_bf16(ACC[2 * i_], ACC[2 * i_ + 1]); \
          PINU(qa, 16); }
        DRAIN_A(S0, 0, PUMP0());
        if (l == 0 && NLAYERS > 1) {
#pragma unroll 1
          for (int rd = 1; rd >= 0; rd--) {
            FOLD(sbase + (12 - rd) * SLOT, rd);
            fence_proxy_async_smem();
            asm volatile("bar.arrive %0, 288;" :: "r"(BAR_WF + 1 - rd) : "memory");
          }
        }
        PUMPS(FPUMP);
        if (l == 0 && NLAYERS > 1) mbar_wait(bar_phi, 1);
#pragma unroll 1
        for (int h = 0; h < 2; h++) {
          const uint32_t pO = sbase + (h ? 3 : 12) * SLOT;
          PROF(4 + h * 12);
          LANE_CONSTS();
          FRAG_PUT(kf + 16, 10); FRAG_PUT(vf + 16, 11);
          STG_ARRIVE();
          if (h) { LOAD_X(); if (AW0) WSTEP(); } else PUMPS(HPUMP2);
          const bool e = g & 1, hb = (2 * t + (g & 1)) <= g;
          uint32_t sel[3] = {e ? 0x1044u : 0x4410u, hb ? 0x4444u : (e ? 0x3244u : 0x4432u), hb ? (e ? 0x3244u : 0x4432u) : 0x4444u};
          PINU(sel, 3);
          TILE_CONSTS(pO, true, O_BIT(l));
          const uint32_t selA = sel[0], selL = sel[1], selH = sel[2];
          STG_WAIT();
          if (warp == 0) mbar_wait(bar_halo, h);
          FRAG_GET(kf, 10);
          PROF(5 + h * 12);
          float s[2][4][4];
#pragma unroll
          for (int ks = 0; ks < 2; ks++)
#pragma unroll
            for (int i = 0; i < 8; i++) {
              const int hh = (i >> 1) & 1, jb = (i & 1) + (~i >> 1 & 2);
              const uint32_t* b = kf + (jb >> 1) * 16 + hh * 8 + ks * 4 + (jb & 1) * 2;
              if (ks) mma_bf16(s[hh][jb], qa[hh * 8 + 4], qa[hh * 8 + 5], qa[hh * 8 + 6], qa[hh * 8 + 7], b[0], b[1]);
              else mma_bf16_z(s[hh][jb], qa[hh * 8], qa[hh * 8 + 1], qa[hh * 8 + 2], qa[hh * 8 + 3], b[0], b[1]);
            }
          PUMP();
          PROF(6 + h * 12);
          float va[2][2], vb[2][2], mx[2][2];
#pragma unroll
          for (int hh = 0; hh < 2; hh++) {
            va[hh][0] = e ? s[hh][1][1] : s[hh][1][0];
            vb[hh][0] = hb ? (e ? s[hh][2][1] : s[hh][2][0]) : (e ? s[hh][0][1] : s[hh][0][0]);
            va[hh][1] = e ? s[hh][2][3] : s[hh][2][2];
            vb[hh][1] = hb ? (e ? s[hh][3][3] : s[hh][3][2]) : (e ? s[hh][1][3] : s[hh][1][2]);
          }
          if (warp == 0 && mm == 0) {
#pragma unroll
            for (int hh = 0; hh < 2; hh++) { va[hh][0] = -INFINITY; if (!hb) { vb[hh][0] = -INFINITY; vb[hh][1] = -INFINITY; } }
          }
#pragma unroll
          for (int i = 0; i < 4; i++) mx[i >> 1][i & 1] = fmaxf(va[i >> 1][i & 1], vb[i >> 1][i & 1]);
#pragma unroll
          for (int o = 1; o <= 2; o <<= 1)
#pragma unroll
            for (int i = 0; i < 4; i++) mx[i >> 1][i & 1] = fmaxf(mx[i >> 1][i & 1], __shfl_xor_sync(0xffffffffu, mx[i >> 1][i & 1], o));
          const float sc0 = rs0 * (0.17677669529663687f * LOG2E), sc1 = rs1 * (0.17677669529663687f * LOG2E);
#pragma unroll
          for (int i = 0; i < 4; i++) {
            const float sc = (i & 1) ? sc1 : sc0, m = mx[i >> 1][i & 1];
            va[i >> 1][i & 1] = ex2((va[i >> 1][i & 1] - m) * sc); vb[i >> 1][i & 1] = ex2((vb[i >> 1][i & 1] - m) * sc);
            mx[i >> 1][i & 1] = va[i >> 1][i & 1] + vb[i >> 1][i & 1];
          }
          if (h == 0 && ASITE) { PIN(&va[0][0], 4); PIN(&vb[0][0], 4); PIN(&mx[0][0], 4); PUMP1(); }
          if (warp == 0) mbar_wait(bar_halo + 8, h);
          FRAG_GET(vf, 11);
#pragma unroll
          for (int o = 1; o <= 2; o <<= 1)
#pragma unroll
            for (int i = 0; i < 4; i++) mx[i >> 1][i & 1] += __shfl_xor_sync(0xffffffffu, mx[i >> 1][i & 1], o);
          float o[2][4][4];
          uint32_t pa[2][8];
#pragma unroll
          for (int hh = 0; hh < 2; hh++) {
            const float i0 = rcp_fast(mx[hh][0]), i1 = rcp_fast(mx[hh][1]);
            const uint32_t w0 = pack_bf16(va[hh][0] * i0, vb[hh][0] * i0), w1 = pack_bf16(va[hh][1] * i1, vb[hh][1] * i1);
            pa[hh][0] = __byte_perm(w0, 0, selL); pa[hh][2] = __byte_perm(w0, 0, selA); pa[hh][3] = __byte_perm(w1, 0, selL);
            pa[hh][4] = __byte_perm(w0, 0, selH); pa[hh][5] = __byte_perm(w1, 0, selA); pa[hh][7] = __byte_perm(w1, 0, selH);
            pa[hh][1] = pa[hh][0] & pa[hh][4]; pa[hh][6] = pa[hh][3] & pa[hh][7];
          }
          PROF(7 + h * 12);
#pragma unroll
          for (int i = 0; i < 8; i++) mma_bf16_z(o[i >> 2][i & 3], pa[i >> 2][4], pa[i >> 2][5], pa[i >> 2][6], pa[i >> 2][7], vf[16 + 2 * i], vf[17 + 2 * i]);
#pragma unroll
          for (int i = 0; i < 8; i++) mma_bf16(o[i >> 2][i & 3], pa[i >> 2][0], pa[i >> 2][1], pa[i >> 2][2], pa[i >> 2][3], vf[2 * i], vf[2 * i + 1]);
          if (h == 0) PUMP1() else mbar_wait(bar_done + 30 * 8, par);
          if (NLAYERS > 1) mbar_wait(bar_phi + 8, 0);
#pragma unroll
          for (int i = 0; i < 4; i++) {
            const int hh = i >> 1, dp = i & 1;
            stsm_x4(ta[i],
                    PBIT0(pack_bf16(o[hh][dp * 2][0], o[hh][dp * 2][1])), PBIT0(pack_bf16(o[hh][dp * 2][2], o[hh][dp * 2][3])),
                    PBIT1(pack_bf16(o[hh][dp * 2 + 1][0], o[hh][dp * 2 + 1][1])), PBIT1(pack_bf16(o[hh][dp * 2 + 1][2], o[hh][dp * 2 + 1][3])));
          }
          PUBLISH_O();
          PROF(11 + h * 12);
          if (h) break;
          REST_P1(ASKEW);
          asm volatile("cp.async.bulk.wait_group.read 0;" ::: "memory");
          DRAIN_A(S1, 1, {});
        }
      } else {
        constexpr uint32_t par = 1;
        float st[32];
        const float c0 = rs0 * LOG2E, c1 = rs1 * LOG2E;
        { V_ADDR(pV); STAGE_V(S0 + 64); }
        if (warp < 2) sts128(sbase + OFF_ONES + warp * 512 + lane * 16, 0x3F803F80u, 0x3F803F80u, 0x3F803F80u, 0x3F803F80u);
        scale32(st, S0, c0, c1);
        PIN(st, 32);
#define KV_MMA(vs) { \
          const uint32_t dp = dA0 + 12 * 1024 - wg * 2560, dv = dA0 + (vs) * 1024 + ((OFF_ONES - (vs) * SLOT - 16) << 12) - wg * (512 << 16); \
          STG_WAIT(); \
          wgmma_fence(); \
          _Pragma("unroll") for (int ks = 0; ks < 8; ks++) { \
            const uint64_t a = DESC(dp + ks * 128, 0x40000040), b = DESC(dv + ks * (64 - (64 << 16)), 0x80000020); \
            if (ks == 0) wgmma_n40<0, 1>(kv, a, b); else wgmma_n40<1, 1>(kv, a, b); } \
          wgmma_commit(); }
#define KV_RED(hp) { \
          float* kvg = g_kv[l >> 1] + (jj * 4 + (hp) * 2) * KVH + warp * 768 + lane * 4; \
          _Pragma("unroll") for (int i = 0; i < 5; i++) red_v4(kvg + i * 128, kv[i * 3], kv[i * 3 + 1], kv[i * 3 + 2], 1.f); \
          red_v4(kvg + 640, kv[15], kv[16], kv[18], 1.f); }
#define KV_LOAD(hp) { \
          const uint4* kvg = reinterpret_cast<const uint4*>(g_kv[l >> 1] + (jj * 4 + (hp) * 2) * KVH) + warp * 192 + lane; \
          _Pragma("unroll") for (int i = 0; i < 6; i++) v[i] = ld_b128(kvg + i * 32); }
#define KVV(i) __uint_as_float((i) % 3 == 0 ? v[(i) / 3].x : ((i) % 3 == 1 ? v[(i) / 3].y : v[(i) / 3].z))
#define KV_TILE(hp) { \
          _Pragma("unroll 1") for (int it = 0; it < (1 << 16); it++) { \
            if (__all_sync(0xffffffffu, (v[0].w & v[1].w & v[2].w & v[3].w & v[4].w & v[5].w) == 0x41800000u)) break; \
            RETRY_COUNT(); \
            KV_LOAD(hp); \
          } \
          PROF(25 + (hp)); \
          const uint32_t e = lane & 7, jt = ((lane >> 1) & 4) + (e >> 1); \
          const uint32_t row = ((((warp >> 1) ^ wg) & 1) << 5) + ((jt & 1) << 4) + ((warp & 1) << 3) + (jt & 6) + (e & 1); \
          const uint32_t kd = pV + wg * 8192 + row * 128, ksw = (row & 7) << 4; \
          _Pragma("unroll") for (int i = 0; i < 2; i++) \
            stsm_x4(kd + ((i * 32 + lhi) ^ ksw), pack_bf16(KVV(i * 8), KVV(i * 8 + 1)), pack_bf16(KVV(i * 8 + 2), KVV(i * 8 + 3)), \
                    pack_bf16(KVV(i * 8 + 4), KVV(i * 8 + 5)), pack_bf16(KVV(i * 8 + 6), KVV(i * 8 + 7))); \
          stsm_x4(kd + ((64u + lhi) ^ ksw), pack_bf16(KVV(16), 1.f), pack_bf16(KVV(17), 1.f), 0u, 0u); }
#pragma unroll 1
        for (int h = 0; h < 2; h++) {
          PROF(4 + h * 2);
          SITE(0);
          LANE_CONSTS();
          const uint32_t dsw = (uint32_t)(g ^ (2 * t)) << 4, dst = ((t & 2) ? pK : sbase + 12 * SLOT) + (r0 + g) * 128;
          float e[16], f[16];
          float sa = exps16_<0>(e, st);
          exps16_fix<0>(e, st, sa);
          asm volatile("" : "+f"(sa)); PIN(e, 16); SITE(1);
          if (h) STG_WAIT();
          store16(e, sa, dst, dsw, 4);
          float sb = exps16_<1>(f, st);
          exps16_fix<1>(f, st, sb);
          asm volatile("" : "+f"(sb)); PIN(f, 16); SITE(2);
          store16(f, sb, dst, dsw, 0);
          float sc = exps16_<0>(e, st + 2);
          exps16_fix<0>(e, st + 2, sc);
          asm volatile("" : "+f"(sc)); PIN(e, 16); SITE(3);
          store16(e, sc, dst + 1024, dsw, 4);
          float sd = exps16_<1>(f, st + 2);
          exps16_fix<1>(f, st + 2, sd);
          asm volatile("" : "+f"(sd)); PIN(f, 16); SITE(4);
          store16(f, sd, dst + 1024, dsw, 0);
          PROF(5 + h * 2);
          if (h) break;
          {
            float kv[20];
            ACC_DEF(kv, 20);
            fence_proxy_async_smem();
            STG_ARRIVE();
            KV_MMA(11);
            PUMP0();
            ACC_FENCE(kv, 20);
            KV_RED(0);
            STG_ARRIVE();
          }
          scale32(st, S0 + 32, c0, c1);
          PIN(st, 32);
        }
        bool big;
        uint32_t fq[32];
        uint4 v[6];
        {
          float kv[20];
          if (KT0) { LANE_CONSTS(); KV_LOAD(0); }
          mbar_wait(bar_stat2, par);
          LNSTEP(S1, 1);
          ub = bar_full + 240;
          PUMP1();
          if (wg == 0) bar_sync<BAR_SKEW, 256>();
          QSTEP(S1, RA_CUR, 1, {});
          if (wg == 1) bar_arrive<BAR_SKEW, 256>();
          QREL();
          if (KT0 == 2) { LANE_CONSTS(); KV_TILE(0); }
          LANE_CONSTS();
          V_ADDR(sbase + 3 * SLOT);
          PINU(va_, 2);
          mbar_wait(bar_done + 30 * 8, par);
          wgmma_wait<0>();
          ACC_FENCE(S1, 96);
          if (!(RLATE & 2)) REL(bar_done + 31 * 8);
          PROF(13);
          STAGE_V(S1 + 64);
          fence_proxy_async_smem();
          STG_ARRIVE();
          if (RLATE & 2) REL(bar_done + 31 * 8);
          scale32(st, S1, c0, c1);
          PIN(st, 32);
          PROF(16);
          ACC_DEF(kv, 20);
          KV_MMA(3);
          SCHED_FENCE();
          if (!KT0) KV_LOAD(0);
          big = any_big(st);
          if (EROT > 0) { expp16<0>(fq, st, big); PINU(fq, 8); }
          if (EROT > 1) { expp16<1>(fq + 8, st, big); PINU(fq + 8, 8); }
          SCHED_FENCE();
          wgmma_wait<0>();
          ACC_FENCE(kv, 20);
          KV_RED(1);
          PROF(17);
        }
#pragma unroll 1
        for (int h = 0; h < 2; h++) {
          const uint32_t pO = sbase + (h ? 3 : 8) * SLOT;
          LANE_CONSTS();
          if (EROT < 1) expp16<0>(fq, st, big);
          if (EROT < 2) expp16<1>(fq + 8, st, big);
          PINU(fq, 16);
          PROF(18 + h * 14);
          SCHED_FENCE();
          if (h) {
            asm volatile("cp.async.bulk.wait_group.read 0;" ::: "memory");
            mbar_wait(bar_lx, par);
          }
          if (h || KT0 < 2) {
            KV_TILE(h);
            fence_proxy_async_smem();
            STG_ARRIVE();
          }
          SCHED_FENCE();
          expp16<0>(fq + 16, st + 16, big); PINU(fq + 16, 8);
          if (h || KT0 < 2) STG_WAIT();
          wgmma_wait<0>();
          ACC_FENCE(S1, 64);
          PROF(19 + h * 14);
          float o[4][20];
#define O_MMA(hh) { \
            const uint64_t db = make_desc(pV + (hh) * 8192, 16, 1024); \
            ACC_DEF(o[(hh) * 2], 20); ACC_DEF(o[(hh) * 2 + 1], 20); \
            wgmma_fence(); \
            wgmma_n40_rs<0>(o[(hh) * 2], fq + (hh) * 16, db + 256); wgmma_n40_rs<0>(o[(hh) * 2 + 1], fq + (hh) * 16 + 8, db); \
            wgmma_n40_rs<1>(o[(hh) * 2], fq + (hh) * 16 + 4, db + 384); wgmma_n40_rs<1>(o[(hh) * 2 + 1], fq + (hh) * 16 + 12, db + 128); \
            wgmma_commit(); }
          O_MMA(0);
          SCHED_FENCE();
          expp16<1>(fq + 24, st + 16, big); PINU(fq + 24, 8);
          SCHED_FENCE();
          PMASKS(true, O_BIT(l));
#pragma unroll
          for (int hh = 0; hh < 2; hh++) {
            if (hh && !OW) O_MMA(1);
            wgmma_wait<0>();
            ACC_FENCE(o[hh * 2], 20); ACC_FENCE(o[hh * 2 + 1], 20);
            if (!hh && OW) { O_MMA(1); SCHED_FENCE(); }
            const float* x = o[hh * 2];
            const float* y = o[hh * 2 + 1];
            const float rx0 = rcp_fast(x[17]), ry0 = rcp_fast(y[17]), rx1 = rcp_fast(x[19]), ry1 = rcp_fast(y[19]);
            const float i0 = rcp_fast(fmaf(x[16], rx0, y[16] * ry0) + 1e-6f), i1 = rcp_fast(fmaf(x[18], rx1, y[18] * ry1) + 1e-6f);
            const float ax0 = rx0 * i0, ay0 = ry0 * i0, ax1 = rx1 * i1, ay1 = ry1 * i1;
#pragma unroll
            for (int dp = 0; dp < 2; dp++)
              stsm_x4(pO + srowoff + ((hh * 64 + dp * 32 + lhi) ^ lsw),
                      PBIT0(pack_bf16(fmaf(x[dp * 8], ax0, y[dp * 8] * ay0), fmaf(x[dp * 8 + 1], ax0, y[dp * 8 + 1] * ay0))),
                      PBIT0(pack_bf16(fmaf(x[dp * 8 + 2], ax1, y[dp * 8 + 2] * ay1), fmaf(x[dp * 8 + 3], ax1, y[dp * 8 + 3] * ay1))),
                      PBIT1(pack_bf16(fmaf(x[dp * 8 + 4], ax0, y[dp * 8 + 4] * ay0), fmaf(x[dp * 8 + 5], ax0, y[dp * 8 + 5] * ay0))),
                      PBIT1(pack_bf16(fmaf(x[dp * 8 + 6], ax1, y[dp * 8 + 6] * ay1), fmaf(x[dp * 8 + 7], ax1, y[dp * 8 + 7] * ay1))));
          }
          PUBLISH_O();
          PROF(20 + h * 14);
          if (h) break;
          if (KVL == 2) { KV_LOAD(1); SCHED_FENCE(); }
          scale32(st, S1 + 32, c0, c1);
          PIN(st, 32);
          LOAD_X();
          bar_wg(wg);
          WSTEP();
          SCHED_FENCE();
          if (KVL == 0) KV_LOAD(1);
          big = any_big(st);
          if (KVL == 1) { SCHED_FENCE(); KV_LOAD(1); }
          if (EROT > 0) { expp16<0>(fq, st, big); PINU(fq, 8); }
          if (EROT > 1) { expp16<1>(fq + 8, st, big); PINU(fq + 8, 8); }
          PROF(31);
        }
      }
      __syncwarp();
      if (elect_one()) mbar_arrive_local(bar_epi);
      bar_wg(wg);
#pragma unroll 1
      while (ub < bar_full + 384) {
        WSTEP();
        if (ub == bar_full + 8 * 41) { asm volatile("cp.async.bulk.wait_group.read 0;" ::: "memory"); PROF(35); }
        if (ub == bar_full + 8 * 42) PROF(36);
      }
      {
        LANE_CONSTS();
        TILE_CONSTS(pK, l < NLAYERS - 1, X_BIT(l));
        wgmma_wait<0>();
        ACC_FENCE(S1, 64);
        if (!RLATE) REL(bar_done + 47 * 8);
        PROF(37);
        X_OUT(0);
        WARP_STORE(l < NLAYERS - 1 ? &tm_os : &tm_xo, pK, jj * 128, mm * 128 + (l < NLAYERS - 1 ? S_LEN : 0));
        if (RLATE) REL(bar_done + 47 * 8);
        if (l == NLAYERS - 1) {
          X_OUT(1);
          WARP_STORE(&tm_xo, pV, jj * 128 + 64, mm * 128);
          if (FINW) asm volatile("cp.async.bulk.wait_group 0;" ::: "memory"); else asm volatile("cp.async.bulk.wait_group.read 0;" ::: "memory");
        }
      }
#pragma unroll
      for (int i = 32; i < 64; i++) { uint32_t c; asm volatile("mov.b32 %0, %1;" : "=r"(c) : "f"(S1[i])); S1[i] = __uint_as_float(c); }
      PROF(38);
    }
    cluster_sync();
  }
}

typedef CUresult (*PFN_encode)(CUtensorMap*, CUtensorMapDataType, cuuint32_t, void*, const cuuint64_t*, const cuuint64_t*,
                               const cuuint32_t*, const cuuint32_t*, CUtensorMapInterleave, CUtensorMapSwizzle,
                               CUtensorMapL2promotion, CUtensorMapFloatOOBfill);

CUtensorMap make_map(PFN_encode enc, const void* ptr, uint64_t inner, uint64_t outer, uint32_t box_inner, uint32_t box_outer,
                     CUtensorMapSwizzle swz = CU_TENSOR_MAP_SWIZZLE_128B) {
  CUtensorMap m;
  cuuint64_t dims[2] = {inner, outer};
  cuuint64_t strides[1] = {inner * 2};
  cuuint32_t box[2] = {box_inner, box_outer};
  cuuint32_t es[2] = {1, 1};
  enc(&m, CU_TENSOR_MAP_DATA_TYPE_BFLOAT16, 2, const_cast<void*>(ptr), dims, strides, box, es, CU_TENSOR_MAP_INTERLEAVE_NONE,
      swz, CU_TENSOR_MAP_L2_PROMOTION_L2_256B, CU_TENSOR_MAP_FLOAT_OOB_FILL_NONE);
  return m;
}

}

extern "C" void kernel_launch(void* const* d_in, const int* in_sizes, int n_in, void* d_out, int out_size) {
  (void)in_sizes; (void)n_in; (void)out_size;
  static PFN_encode enc = nullptr;
  if (!enc) {
    void* fn = nullptr;
    cudaDriverEntryPointQueryResult qr;
    cudaGetDriverEntryPoint("cuTensorMapEncodeTiled", &fn, cudaEnableDefault, &qr);
    enc = (PFN_encode)fn;
    cudaFuncSetAttribute(mega_kernel, cudaFuncAttributeMaxDynamicSharedMemorySize, SMEM_BYTES);
  }
  Params prm;
  prm.x0 = (const __nv_bfloat16*)d_in[0];
  prm.wA_qkv = (const __nv_bfloat16*)d_in[1];
  prm.wA_o = (const __nv_bfloat16*)d_in[2];
  prm.wB_qkv = (const __nv_bfloat16*)d_in[4];
  prm.wB_phi = (const __nv_bfloat16*)d_in[5];
  prm.wB_o = (const __nv_bfloat16*)d_in[6];
  prm.out = (__nv_bfloat16*)d_out;
  void *obuf = nullptr, *wf = nullptr;
  cudaGetSymbolAddress(&obuf, g_obuf);
  cudaGetSymbolAddress(&wf, g_wfold);
  CUtensorMap tm_x0 = make_map(enc, d_in[0], D_MODEL, S_LEN, 64, 128);
  CUtensorMap tm_xo = make_map(enc, d_out, D_MODEL, S_LEN, 64, 16);
  CUtensorMap tm_os = make_map(enc, obuf, D_MODEL, 2 * S_LEN, 64, 16);
  CUtensorMap tm_o = make_map(enc, obuf, D_MODEL, 2 * S_LEN, 64, 128);
  CUtensorMap tm_wf = make_map(enc, wf, 2048, D_MODEL, 64, 32);
  CUtensorMap tm_wqA = make_map(enc, d_in[1], 3 * D_MODEL, D_MODEL, 64, 32);
  CUtensorMap tm_wqB = make_map(enc, prm.wB_qkv, 3 * D_MODEL, D_MODEL, 64, 32);
  CUtensorMap tm_woA = make_map(enc, prm.wA_o, D_MODEL, D_MODEL, 64, 64);
  CUtensorMap tm_woB = make_map(enc, prm.wB_o, D_MODEL, D_MODEL, 64, 64);
  CUtensorMap tm_phi = make_map(enc, prm.wB_phi, 32, 1024, 32, 128, CU_TENSOR_MAP_SWIZZLE_64B);
  mega_kernel<<<NMAIN + NAUX, 384, SMEM_BYTES>>>(tm_x0, tm_xo, tm_os, tm_o, tm_wf, tm_wqA, tm_wqB, tm_woA, tm_woB, tm_phi, prm);
}
```

```cpp
#include <cuda_runtime.h>
#include <cuda.h>
#include <cuda_bf16.h>
#include <stdint.h>

#define NLAYERS 4

#define STAG1 0
#define HPUMP1 2
#define HPUMP2 1
#define ASKEW 2
#define FPUMP 3
#define PFGAP 100
#define POLLGAP 120
#define OW 1
#define AW0 1
#define RLATE 3
#define FSTART 0
#define MAPV 1
#define HW1 29
#define XPACE 0x06050401000000ull
#define XP0 4
#define HW0 18
#define XD 4
#define WFGAP 50
#define KT0 2
#define W23 0
#define AX 0
#define PF0 1
#define EARLY 2
#define BIGLIM 3600.f
#define SUMLO 0x1p-100f
#define SUMHI 0x1p100f
#define EROT 1
#define FINW 0
#define AHOIST 1
#define KVL 1
#define BMASK 0x1F
#define ASITE 1
namespace {

constexpr int S_LEN = 2048, D_MODEL = 1024;
constexpr int NAUX = 4, NMAIN = 128;
constexpr int SLOT = 16384;
constexpr int QST = 24576;
constexpr int OFF_RA = 6 * SLOT, OFF_S = 10 * SLOT;
constexpr int OFF_HALO = 13 * SLOT, OFF_LNB = OFF_HALO  , OFF_ONES = OFF_HALO + 3072;
constexpr int OFF_ST = OFF_HALO + 7168  , OFF_PHI = OFF_HALO + 8192;
constexpr int OFF_BAR = 14 * SLOT;
constexpr int OFF_LNA = OFF_BAR + 1024;
constexpr int SMEM_BYTES = OFF_LNA + 2048;
#define WO_ASLOT(par) ((par) ? 0x9876CAB39876CA98ull : 0x98C76BA398C7698Cull)
constexpr unsigned long long WO_BSLOT = 0x5432105421054210ull;
__device__ __forceinline__ int srcb(int j, int i) { return (i + (i >= j)) & 7; }
__device__ __forceinline__ int kslice(int j, int i) { return i < 2 ? 2 * j + i : (i < 9 ? 2 * srcb(j, i - 2) : 2 * srcb(j, i - 9) + 1); }
__device__ __forceinline__ int wslice(int j, int s) { return 2 * ((s & 7) ? srcb(j, (s & 7) - 1) : j) + (s >> 3); }
constexpr int KVH = 6 * 128 * 4;

struct __align__(128) Flag { unsigned v; unsigned pad[31]; };
struct Flags {
  Flag xready[4][16];
  Flag wfready[8];
  Flag done;
  Flag epoch;
};

__device__ Flags g_flags;
__device__ __nv_bfloat16 g_obuf[2 * S_LEN * D_MODEL];
#define O_BIT(l) ((epoch * NLAYERS + (l) + 1) & 1u)
#define X_BIT(l) ((epoch * (NLAYERS - 1) + (l) + 1) & 1u)
__device__ __nv_bfloat16 g_wfold[D_MODEL * 2048];
__device__ uint4 g_halo[16 * 8 * 512];
__device__ __align__(128) float g_kv[2][32 * KVH];
__device__ __align__(128) uint2 g_colsum[2][1536][2];
__device__ __align__(128) uint2 g_stats[S_LEN * 8];
#define H_BIT(l) (NLAYERS > 2 ? (uint32_t)((l) == 0) : (ep1 & 1))
#define STAT_TAG(l) ((ep1 * NLAYERS + (l) + 1) & 3u)

#define RETRY_COUNT()
#define PRL 0
#define PRU 0
#define PROFL 1
#define PROFW 0
#define PROFT(i) do {} while (0)
#define PROF(i) do {} while (0)

__device__ __forceinline__ uint32_t smem_u32(const void* p) { return (uint32_t)__cvta_generic_to_shared(p); }
__device__ __forceinline__ bool elect_one() {
  uint32_t p;
  asm volatile("{\n.reg .pred p;\nelect.sync _|p, 0xffffffff;\nselp.u32 %0, 1, 0, p;\n}\n" : "=r"(p));
  return p != 0;
}
__device__ __forceinline__ void mbar_init(uint32_t bar, uint32_t cnt) {
  asm volatile("mbarrier.init.shared::cta.b64 [%0], %1;" :: "r"(bar), "r"(cnt));
}
__device__ __forceinline__ void mbar_expect_tx(uint32_t bar, uint32_t bytes) {
  asm volatile("mbarrier.arrive.expect_tx.shared::cta.b64 _, [%0], %1;" :: "r"(bar), "r"(bytes) : "memory");
}
#define mbar_wait(bar, parity) \
  asm volatile("{\n.reg .pred p, q;\nW_%=:\nmbarrier.try_wait.parity.shared::cta.b64 p, [%1], %2;\nadd.s32 %0, %0, -1;\n" \
               "setp.gt.and.s32 q, %0, 0, !p;\n@q bra.uni W_%=;\n}\n" : "+r"(budget) : "r"((uint32_t)(bar)), "r"((uint32_t)(parity)) : "memory")
#define mbar_wait_sl(bar, parity) \
  asm volatile("{\n.reg .pred p, q;\nW_%=:\nmbarrier.try_wait.parity.shared::cta.b64 p, [%1], %2, 20000;\nadd.s32 %0, %0, -64;\n" \
               "setp.gt.and.s32 q, %0, 0, !p;\n@q bra.uni W_%=;\n}\n" : "+r"(budget) : "r"((uint32_t)(bar)), "r"((uint32_t)(parity)) : "memory")
__device__ __forceinline__ void mbar_arrive_local(uint32_t bar) {
  asm volatile("mbarrier.arrive.shared::cta.b64 _, [%0];" :: "r"(bar) : "memory");
}
__device__ __forceinline__ void tma_load_2d(uint32_t dst, const CUtensorMap* tm, uint32_t bar, int c0, int c1) {
  asm volatile("cp.async.bulk.tensor.2d.shared::cluster.global.mbarrier::complete_tx::bytes [%0], [%1, {%3, %4}], [%2];"
               :: "r"(dst), "l"(tm), "r"(bar), "r"(c0), "r"(c1) : "memory");
}
__device__ __forceinline__ void tma_load_2d_mc(uint32_t dst, const CUtensorMap* tm, uint32_t bar, int c0, int c1) {
  asm volatile("cp.async.bulk.tensor.2d.shared::cluster.global.mbarrier::complete_tx::bytes.multicast::cluster [%0], [%1, {%3, %4}], [%2], %5;"
               :: "r"(dst), "l"(tm), "r"(bar), "r"(c0), "r"(c1), "h"((uint16_t)3) : "memory");
}
__device__ __forceinline__ void tma_store_2d(const CUtensorMap* tm, uint32_t src, int c0, int c1) {
  asm volatile("cp.async.bulk.tensor.2d.global.shared::cta.bulk_group [%0, {%2, %3}], [%1];"
               :: "l"(tm), "r"(src), "r"(c0), "r"(c1) : "memory");
}
__device__ __forceinline__ void bulk_commit_wait() {
  asm volatile("cp.async.bulk.commit_group;\ncp.async.bulk.wait_group 0;" ::: "memory");
}
__device__ __forceinline__ void prefetch_tmap(const CUtensorMap* tm) {
  asm volatile("prefetch.tensormap [%0];" :: "l"(tm) : "memory");
}
__device__ __forceinline__ void fence_proxy_async_global() { asm volatile("fence.proxy.async.global;" ::: "memory"); }
__device__ __forceinline__ void fence_proxy_async_smem() { asm volatile("fence.proxy.async.shared::cta;" ::: "memory"); }
__device__ __forceinline__ unsigned ld_relaxed(const unsigned* p) {
  unsigned v;
  asm volatile("ld.relaxed.gpu.global.u32 %0, [%1];" : "=r"(v) : "l"(p) : "memory");
  return v;
}
__device__ __forceinline__ void fence_acquire() { asm volatile("fence.acquire.gpu;" ::: "memory"); }
__device__ __forceinline__ void wait_flag(const unsigned* p, unsigned target) {
  int it = 0;
  while ((int)(ld_relaxed(p) - target) < 0 && ++it < (1 << 20)) {}
  fence_acquire();
}
__device__ __forceinline__ void signal_release(unsigned* p) {
  asm volatile("red.release.gpu.global.add.u32 [%0], 1;" :: "l"(p) : "memory");
}
template <int ID, int N> __device__ __forceinline__ void bar_arrive() { asm volatile("bar.arrive %0, %1;" :: "n"(ID), "n"(N) : "memory"); }
template <int ID, int N> __device__ __forceinline__ void bar_sync() { asm volatile("bar.sync %0, %1;" :: "n"(ID), "n"(N) : "memory"); }
__device__ __forceinline__ void bar_wg(int wg) { asm volatile("bar.sync %0, 128;" :: "r"(2 + wg) : "memory"); }
__device__ __forceinline__ void cluster_sync() {
  asm volatile("barrier.cluster.arrive.relaxed.aligned;\nbarrier.cluster.wait.aligned;" ::: "memory");
}
__device__ __forceinline__ void cluster_wait() { asm volatile("barrier.cluster.wait.acquire.aligned;" ::: "memory"); }
enum { BAR_X1 = 7, BAR_WF = 8  , BAR_SKEW = 10 };

__device__ __forceinline__ void wgmma_fence() { asm volatile("wgmma.fence.sync.aligned;" ::: "memory"); }
__device__ __forceinline__ void wgmma_commit() { asm volatile("wgmma.commit_group.sync.aligned;" ::: "memory"); }
template <int N> __device__ __forceinline__ void wgmma_wait() { asm volatile("wgmma.wait_group.sync.aligned %0;" :: "n"(N) : "memory"); }

template <int scale_d, int tnsp_b = 1> __device__ __forceinline__ void wgmma_n192(float* d, uint64_t descA, uint64_t descB) {
  asm volatile("{\n.reg .pred p;\nsetp.ne.b32 p, %98, 0;\n"
               "wgmma.mma_async.sync.aligned.m64n192k16.f32.bf16.bf16 {%0,%1,%2,%3,%4,%5,%6,%7,%8,%9,%10,%11,%12,%13,%14,%15,%16,%17,%18,%19,%20,%21,%22,%23,%24,%25,%26,%27,%28,%29,%30,%31,%32,%33,%34,%35,%36,%37,%38,%39,%40,%41,%42,%43,%44,%45,%46,%47,%48,%49,%50,%51,%52,%53,%54,%55,%56,%57,%58,%59,%60,%61,%62,%63,%64,%65,%66,%67,%68,%69,%70,%71,%72,%73,%74,%75,%76,%77,%78,%79,%80,%81,%82,%83,%84,%85,%86,%87,%88,%89,%90,%91,%92,%93,%94,%95}, %96, %97, p, 1, 1, 0, %99;\n}\n"
               : "+f"(d[0]), "+f"(d[1]), "+f"(d[2]), "+f"(d[3]), "+f"(d[4]), "+f"(d[5]), "+f"(d[6]), "+f"(d[7]), "+f"(d[8]), "+f"(d[9]), "+f"(d[10]), "+f"(d[11]), "+f"(d[12]), "+f"(d[13]), "+f"(d[14]), "+f"(d[15]), "+f"(d[16]), "+f"(d[17]), "+f"(d[18]), "+f"(d[19]), "+f"(d[20]), "+f"(d[21]), "+f"(d[22]), "+f"(d[23]), "+f"(d[24]), "+f"(d[25]), "+f"(d[26]), "+f"(d[27]), "+f"(d[28]), "+f"(d[29]), "+f"(d[30]), "+f"(d[31]), "+f"(d[32]), "+f"(d[33]), "+f"(d[34]), "+f"(d[35]), "+f"(d[36]), "+f"(d[37]), "+f"(d[38]), "+f"(d[39]), "+f"(d[40]), "+f"(d[41]), "+f"(d[42]), "+f"(d[43]), "+f"(d[44]), "+f"(d[45]), "+f"(d[46]), "+f"(d[47]), "+f"(d[48]), "+f"(d[49]), "+f"(d[50]), "+f"(d[51]), "+f"(d[52]), "+f"(d[53]), "+f"(d[54]), "+f"(d[55]), "+f"(d[56]), "+f"(d[57]), "+f"(d[58]), "+f"(d[59]), "+f"(d[60]), "+f"(d[61]), "+f"(d[62]), "+f"(d[63]), "+f"(d[64]), "+f"(d[65]), "+f"(d[66]), "+f"(d[67]), "+f"(d[68]), "+f"(d[69]), "+f"(d[70]), "+f"(d[71]), "+f"(d[72]), "+f"(d[73]), "+f"(d[74]), "+f"(d[75]), "+f"(d[76]), "+f"(d[77]), "+f"(d[78]), "+f"(d[79]), "+f"(d[80]), "+f"(d[81]), "+f"(d[82]), "+f"(d[83]), "+f"(d[84]), "+f"(d[85]), "+f"(d[86]), "+f"(d[87]), "+f"(d[88]), "+f"(d[89]), "+f"(d[90]), "+f"(d[91]), "+f"(d[92]), "+f"(d[93]), "+f"(d[94]), "+f"(d[95])
               : "l"(descA), "l"(descB), "n"(scale_d), "n"(tnsp_b));
}
template <int scale_d> __device__ __forceinline__ void wgmma4_n192(float* d, uint32_t da, uint32_t db) {
#define R_ "{%0,%1,%2,%3,%4,%5,%6,%7,%8,%9,%10,%11,%12,%13,%14,%15,%16,%17,%18,%19,%20,%21,%22,%23,%24,%25,%26,%27,%28,%29,%30,%31,%32,%33,%34,%35,%36,%37,%38,%39,%40,%41,%42,%43,%44,%45,%46,%47,%48,%49,%50,%51,%52,%53,%54,%55,%56,%57,%58,%59,%60,%61,%62,%63,%64,%65,%66,%67,%68,%69,%70,%71,%72,%73,%74,%75,%76,%77,%78,%79,%80,%81,%82,%83,%84,%85,%86,%87,%88,%89,%90,%91,%92,%93,%94,%95}"
  asm volatile("{\n.reg .pred p, q;\n.reg .b64 a, b;\nsetp.ne.b32 p, %98, 0;\nsetp.eq.b32 q, 0, 0;\nmov.b64 a, {%96, 0x40000040};\nmov.b64 b, {%97, 0x40000040};\n"
               "wgmma.mma_async.sync.aligned.m64n192k16.f32.bf16.bf16 " R_ ", a, b, p, 1, 1, 0, 1;\nadd.s64 a, a, 2;\nadd.s64 b, b, 128;\n"
               "wgmma.mma_async.sync.aligned.m64n192k16.f32.bf16.bf16 " R_ ", a, b, q, 1, 1, 0, 1;\nadd.s64 a, a, 2;\nadd.s64 b, b, 128;\n"
               "wgmma.mma_async.sync.aligned.m64n192k16.f32.bf16.bf16 " R_ ", a, b, q, 1, 1, 0, 1;\nadd.s64 a, a, 2;\nadd.s64 b, b, 128;\n"
               "wgmma.mma_async.sync.aligned.m64n192k16.f32.bf16.bf16 " R_ ", a, b, q, 1, 1, 0, 1;\n}\n"
               : "+f"(d[0]), "+f"(d[1]), "+f"(d[2]), "+f"(d[3]), "+f"(d[4]), "+f"(d[5]), "+f"(d[6]), "+f"(d[7]), "+f"(d[8]), "+f"(d[9]), "+f"(d[10]), "+f"(d[11]), "+f"(d[12]), "+f"(d[13]), "+f"(d[14]), "+f"(d[15]), "+f"(d[16]), "+f"(d[17]), "+f"(d[18]), "+f"(d[19]), "+f"(d[20]), "+f"(d[21]), "+f"(d[22]), "+f"(d[23]), "+f"(d[24]), "+f"(d[25]), "+f"(d[26]), "+f"(d[27]), "+f"(d[28]), "+f"(d[29]), "+f"(d[30]), "+f"(d[31]), "+f"(d[32]), "+f"(d[33]), "+f"(d[34]), "+f"(d[35]), "+f"(d[36]), "+f"(d[37]), "+f"(d[38]), "+f"(d[39]), "+f"(d[40]), "+f"(d[41]), "+f"(d[42]), "+f"(d[43]), "+f"(d[44]), "+f"(d[45]), "+f"(d[46]), "+f"(d[47]), "+f"(d[48]), "+f"(d[49]), "+f"(d[50]), "+f"(d[51]), "+f"(d[52]), "+f"(d[53]), "+f"(d[54]), "+f"(d[55]), "+f"(d[56]), "+f"(d[57]), "+f"(d[58]), "+f"(d[59]), "+f"(d[60]), "+f"(d[61]), "+f"(d[62]), "+f"(d[63]), "+f"(d[64]), "+f"(d[65]), "+f"(d[66]), "+f"(d[67]), "+f"(d[68]), "+f"(d[69]), "+f"(d[70]), "+f"(d[71]), "+f"(d[72]), "+f"(d[73]), "+f"(d[74]), "+f"(d[75]), "+f"(d[76]), "+f"(d[77]), "+f"(d[78]), "+f"(d[79]), "+f"(d[80]), "+f"(d[81]), "+f"(d[82]), "+f"(d[83]), "+f"(d[84]), "+f"(d[85]), "+f"(d[86]), "+f"(d[87]), "+f"(d[88]), "+f"(d[89]), "+f"(d[90]), "+f"(d[91]), "+f"(d[92]), "+f"(d[93]), "+f"(d[94]), "+f"(d[95])
               : "r"(da), "r"(db), "n"(scale_d));
#undef R_
}
template <int scale_d> __device__ __forceinline__ void wgmma4_n128(float* d, uint32_t da, uint32_t db) {
#define R_ "{%0,%1,%2,%3,%4,%5,%6,%7,%8,%9,%10,%11,%12,%13,%14,%15,%16,%17,%18,%19,%20,%21,%22,%23,%24,%25,%26,%27,%28,%29,%30,%31,%32,%33,%34,%35,%36,%37,%38,%39,%40,%41,%42,%43,%44,%45,%46,%47,%48,%49,%50,%51,%52,%53,%54,%55,%56,%57,%58,%59,%60,%61,%62,%63}"
  asm volatile("{\n.reg .pred p, q;\n.reg .b64 a, b;\nsetp.ne.b32 p, %66, 0;\nsetp.eq.b32 q, 0, 0;\nmov.b64 a, {%64, 0x40000040};\nmov.b64 b, {%65, 0x40000040};\n"
               "wgmma.mma_async.sync.aligned.m64n128k16.f32.bf16.bf16 " R_ ", a, b, p, 1, 1, 0, 1;\nadd.s64 a, a, 2;\nadd.s64 b, b, 128;\n"
               "wgmma.mma_async.sync.aligned.m64n128k16.f32.bf16.bf16 " R_ ", a, b, q, 1, 1, 0, 1;\nadd.s64 a, a, 2;\nadd.s64 b, b, 128;\n"
               "wgmma.mma_async.sync.aligned.m64n128k16.f32.bf16.bf16 " R_ ", a, b, q, 1, 1, 0, 1;\nadd.s64 a, a, 2;\nadd.s64 b, b, 128;\n"
               "wgmma.mma_async.sync.aligned.m64n128k16.f32.bf16.bf16 " R_ ", a, b, q, 1, 1, 0, 1;\n}\n"
               : "+f"(d[0]), "+f"(d[1]), "+f"(d[2]), "+f"(d[3]), "+f"(d[4]), "+f"(d[5]), "+f"(d[6]), "+f"(d[7]), "+f"(d[8]), "+f"(d[9]), "+f"(d[10]), "+f"(d[11]), "+f"(d[12]), "+f"(d[13]), "+f"(d[14]), "+f"(d[15]), "+f"(d[16]), "+f"(d[17]), "+f"(d[18]), "+f"(d[19]), "+f"(d[20]), "+f"(d[21]), "+f"(d[22]), "+f"(d[23]), "+f"(d[24]), "+f"(d[25]), "+f"(d[26]), "+f"(d[27]), "+f"(d[28]), "+f"(d[29]), "+f"(d[30]), "+f"(d[31]), "+f"(d[32]), "+f"(d[33]), "+f"(d[34]), "+f"(d[35]), "+f"(d[36]), "+f"(d[37]), "+f"(d[38]), "+f"(d[39]), "+f"(d[40]), "+f"(d[41]), "+f"(d[42]), "+f"(d[43]), "+f"(d[44]), "+f"(d[45]), "+f"(d[46]), "+f"(d[47]), "+f"(d[48]), "+f"(d[49]), "+f"(d[50]), "+f"(d[51]), "+f"(d[52]), "+f"(d[53]), "+f"(d[54]), "+f"(d[55]), "+f"(d[56]), "+f"(d[57]), "+f"(d[58]), "+f"(d[59]), "+f"(d[60]), "+f"(d[61]), "+f"(d[62]), "+f"(d[63])
               : "r"(da), "r"(db), "n"(scale_d));
#undef R_
}
template <int scale_d> __device__ __forceinline__ void wgmma_n32(float* d, uint64_t descA, uint64_t descB) {
  asm volatile("{\n.reg .pred p;\nsetp.ne.b32 p, %18, 0;\n"
               "wgmma.mma_async.sync.aligned.m64n32k16.f32.bf16.bf16 {%0,%1,%2,%3,%4,%5,%6,%7,%8,%9,%10,%11,%12,%13,%14,%15}, %16, %17, p, 1, 1, 0, 1;\n}\n"
               : "+f"(d[0]), "+f"(d[1]), "+f"(d[2]), "+f"(d[3]), "+f"(d[4]), "+f"(d[5]), "+f"(d[6]), "+f"(d[7]), "+f"(d[8]), "+f"(d[9]), "+f"(d[10]), "+f"(d[11]), "+f"(d[12]), "+f"(d[13]), "+f"(d[14]), "+f"(d[15])
               : "l"(descA), "l"(descB), "n"(scale_d));
}
template <int scale_d, int tnsp_a> __device__ __forceinline__ void wgmma_n40(float* d, uint64_t descA, uint64_t descB) {
  asm volatile("{\n.reg .pred p;\nsetp.ne.b32 p, %22, 0;\n"
               "wgmma.mma_async.sync.aligned.m64n40k16.f32.bf16.bf16 {%0,%1,%2,%3,%4,%5,%6,%7,%8,%9,%10,%11,%12,%13,%14,%15,%16,%17,%18,%19}, %20, %21, p, 1, 1, %23, 1;\n}\n"
               : "+f"(d[0]), "+f"(d[1]), "+f"(d[2]), "+f"(d[3]), "+f"(d[4]), "+f"(d[5]), "+f"(d[6]), "+f"(d[7]), "+f"(d[8]), "+f"(d[9]), "+f"(d[10]), "+f"(d[11]), "+f"(d[12]), "+f"(d[13]), "+f"(d[14]), "+f"(d[15]), "+f"(d[16]), "+f"(d[17]), "+f"(d[18]), "+f"(d[19])
               : "l"(descA), "l"(descB), "n"(scale_d), "n"(tnsp_a));
}
template <int scale_d> __device__ __forceinline__ void wgmma_n40_rs(float* d, const uint32_t* a, uint64_t descB) {
  asm volatile("{\n.reg .pred p;\nsetp.ne.b32 p, %25, 0;\n"
               "wgmma.mma_async.sync.aligned.m64n40k16.f32.bf16.bf16 {%0,%1,%2,%3,%4,%5,%6,%7,%8,%9,%10,%11,%12,%13,%14,%15,%16,%17,%18,%19}, {%20,%21,%22,%23}, %24, p, 1, 1, 1;\n}\n"
               : "+f"(d[0]), "+f"(d[1]), "+f"(d[2]), "+f"(d[3]), "+f"(d[4]), "+f"(d[5]), "+f"(d[6]), "+f"(d[7]), "+f"(d[8]), "+f"(d[9]), "+f"(d[10]), "+f"(d[11]), "+f"(d[12]), "+f"(d[13]), "+f"(d[14]), "+f"(d[15]), "+f"(d[16]), "+f"(d[17]), "+f"(d[18]), "+f"(d[19])
               : "r"(a[0]), "r"(a[1]), "r"(a[2]), "r"(a[3]), "l"(descB), "n"(scale_d));
}
__device__ __forceinline__ uint64_t make_desc(uint32_t addr, uint32_t lbo_bytes, uint32_t sbo_bytes) {
  return (uint64_t)((addr & 0x3FFFF) >> 4) | ((uint64_t)(lbo_bytes >> 4) << 16) | ((uint64_t)(sbo_bytes >> 4) << 32) | (1ull << 62);
}

__device__ __forceinline__ void ldsm_x4(uint32_t addr, uint32_t& r0, uint32_t& r1, uint32_t& r2, uint32_t& r3) {
  asm volatile("ldmatrix.sync.aligned.m8n8.x4.shared.b16 {%0,%1,%2,%3}, [%4];" : "=r"(r0), "=r"(r1), "=r"(r2), "=r"(r3) : "r"(addr) : "memory");
}
__device__ __forceinline__ void ldsm_x4_t(uint32_t addr, uint32_t& r0, uint32_t& r1, uint32_t& r2, uint32_t& r3) {
  asm volatile("ldmatrix.sync.aligned.m8n8.x4.trans.shared.b16 {%0,%1,%2,%3}, [%4];" : "=r"(r0), "=r"(r1), "=r"(r2), "=r"(r3) : "r"(addr) : "memory");
}
__device__ __forceinline__ void stsm_x4(uint32_t addr, uint32_t r0, uint32_t r1, uint32_t r2, uint32_t r3) {
  asm volatile("stmatrix.sync.aligned.m8n8.x4.shared.b16 [%0], {%1,%2,%3,%4};" :: "r"(addr), "r"(r0), "r"(r1), "r"(r2), "r"(r3) : "memory");
}
__device__ __forceinline__ void sts128(uint32_t addr, uint32_t a, uint32_t b, uint32_t c, uint32_t d) {
  asm volatile("st.shared.v4.u32 [%0], {%1,%2,%3,%4};" :: "r"(addr), "r"(a), "r"(b), "r"(c), "r"(d) : "memory");
}
__device__ __forceinline__ float lds32f(uint32_t addr) {
  float v;
  asm volatile("ld.shared.f32 %0, [%1];" : "=f"(v) : "r"(addr) : "memory");
  return v;
}
__device__ __forceinline__ void sts32f(uint32_t addr, float a) {
  asm volatile("st.shared.f32 [%0], %1;" :: "r"(addr), "f"(a) : "memory");
}
__device__ __forceinline__ void mma_bf16(float (&c)[4], uint32_t a0, uint32_t a1, uint32_t a2, uint32_t a3, uint32_t b0, uint32_t b1) {
  asm volatile("mma.sync.aligned.m16n8k16.row.col.f32.bf16.bf16.f32 {%0,%1,%2,%3}, {%4,%5,%6,%7}, {%8,%9}, {%0,%1,%2,%3};"
               : "+f"(c[0]), "+f"(c[1]), "+f"(c[2]), "+f"(c[3]) : "r"(a0), "r"(a1), "r"(a2), "r"(a3), "r"(b0), "r"(b1));
}
__device__ __forceinline__ void mma_bf16_z(float (&c)[4], uint32_t a0, uint32_t a1, uint32_t a2, uint32_t a3, uint32_t b0, uint32_t b1) {
  asm volatile("mma.sync.aligned.m16n8k16.row.col.f32.bf16.bf16.f32 {%0,%1,%2,%3}, {%4,%5,%6,%7}, {%8,%9}, {%10,%10,%10,%10};"
               : "=f"(c[0]), "=f"(c[1]), "=f"(c[2]), "=f"(c[3]) : "r"(a0), "r"(a1), "r"(a2), "r"(a3), "r"(b0), "r"(b1), "f"(0.f));
}
__device__ __forceinline__ uint32_t movm_t(uint32_t v) {
  uint32_t r;
  asm volatile("movmatrix.sync.aligned.m8n8.trans.b16 %0, %1;" : "=r"(r) : "r"(v));
  return r;
}
__device__ __forceinline__ uint32_t pack_bf16(float lo, float hi) {
  uint32_t r;
  asm("cvt.rn.bf16x2.f32 %0, %1, %2;" : "=r"(r) : "f"(hi), "f"(lo));
  return r;
}
__device__ __forceinline__ float bf_lo(uint32_t v) { return __uint_as_float(v << 16); }
__device__ __forceinline__ float bf_hi(uint32_t v) { return __uint_as_float(v & 0xFFFF0000u); }
__device__ __forceinline__ void split3(float x, uint32_t& h, uint32_t& m, uint32_t& l) {
  h = pack_bf16(x, 0.f); x -= bf_lo(h);
  m = pack_bf16(x, 0.f); x -= bf_lo(m);
  l = pack_bf16(x, 0.f);
}
__device__ __forceinline__ float ex2(float x) { float r; asm("ex2.approx.ftz.f32 %0, %1;" : "=f"(r) : "f"(x)); return r; }
__device__ __forceinline__ float rcp_fast(float x) { float r; asm("rcp.approx.ftz.f32 %0, %1;" : "=f"(r) : "f"(x)); return r; }
__device__ __forceinline__ void red_v4(float* p, float a, float b, float c, float d) {
  asm volatile("red.global.add.v4.f32 [%0], {%1, %2, %3, %4};" :: "l"(p), "f"(a), "f"(b), "f"(c), "f"(d) : "memory");
}
__device__ __forceinline__ uint4 ld_ll(const uint4* p) {
  uint4 v;
  asm volatile("{\n.reg .b64 a, b;\nld.relaxed.gpu.global.v2.b64 {a, b}, [%4];\nmov.b64 {%0, %1}, a;\nmov.b64 {%2, %3}, b;\n}\n"
               : "=r"(v.x), "=r"(v.y), "=r"(v.z), "=r"(v.w) : "l"(p) : "memory");
  return v;
}
__device__ __forceinline__ void st_b64(uint2* p, uint32_t a, uint32_t b) {
  asm volatile("{\n.reg .b64 v;\nmov.b64 v, {%1, %2};\nst.relaxed.gpu.global.b64 [%0], v;\n}\n" :: "l"(p), "r"(a), "r"(b) : "memory");
}
__device__ __forceinline__ void st_b128(uint4* p, uint32_t a, uint32_t b, uint32_t c, uint32_t d) {
  asm volatile("{\n.reg .b128 v;\nmov.b128 v, {%1, %2, %3, %4};\nst.relaxed.gpu.global.b128 [%0], v;\n}\n" :: "l"(p), "r"(a), "r"(b), "r"(c), "r"(d) : "memory");
}
__device__ __forceinline__ uint4 ld_b128(const uint4* p) {
  uint4 v;
  asm volatile("{\n.reg .b128 v;\nld.relaxed.gpu.global.b128 v, [%4];\nmov.b128 {%0, %1, %2, %3}, v;\n}\n" : "=r"(v.x), "=r"(v.y), "=r"(v.z), "=r"(v.w) : "l"(p) : "memory");
  return v;
}

constexpr float LOG2E = 1.4426950408889634f;

struct Params {
  const __nv_bfloat16* x0;
  const __nv_bfloat16* wA_qkv;
  const __nv_bfloat16* wA_o;
  const __nv_bfloat16* wB_qkv;
  const __nv_bfloat16* wB_phi;
  const __nv_bfloat16* wB_o;
  __nv_bfloat16* out;
};

#define ACC_DEF(d, n) _Pragma("unroll") for (int i_ = 0; i_ < (n); i_++) asm volatile("" : "=f"(d[i_]))
#define ACC_FENCE(d, n) _Pragma("unroll") for (int i_ = 0; i_ < (n); i_++) asm volatile("" : "+f"(d[i_]) :: "memory")
#define PIN(a, n) _Pragma("unroll") for (int i_ = 0; i_ < (n); i_++) asm volatile("" : "+f"((a)[i_]))
#define PINU(a, n) _Pragma("unroll") for (int i_ = 0; i_ < (n); i_++) asm volatile("" : "+r"((a)[i_]))

#define V_ADDR(p0) uint32_t va_[2] = {(p0) + (srowoff >> 1) + (lhi ^ lsw2), (p0) + (srowoff >> 1) + ((32 + lhi) ^ lsw2)}
#define STAGE_V(acc) { \
    _Pragma("unroll") for (int j_ = 0; j_ < 4; j_++) { \
      const float* a_ = (acc) + j_ * 8; \
      stsm_x4(va_[j_ & 1] + (j_ >> 1) * 8192, \
              pack_bf16(rs0 * a_[0], rs0 * a_[1]), pack_bf16(rs1 * a_[2], rs1 * a_[3]), pack_bf16(rs0 * a_[4], rs0 * a_[5]), pack_bf16(rs1 * a_[6], rs1 * a_[7])); } }
#define FRAG(dst, acc, TR, grp) { \
    _Pragma("unroll") for (int i_ = 0; i_ < 16; i_++) { \
      const float r_ = (i_ & 1) ? rs1 : rs0; \
      const uint32_t w_ = pack_bf16(r_ * (acc)[2 * i_], r_ * (acc)[2 * i_ + 1]); \
      if (TR) (dst)[i_] = movm_t(w_); else (dst)[(i_ & 12) + (i_ & 1) * 2 + ((i_ >> 1) & 1)] = w_; } \
    if (warp == 7 && mm < 15) { \
      _Pragma("unroll") for (int j_ = 0; j_ < 4; j_++) \
        st_b128(g_halo + (size_t)(mm * 8 + jj) * 512 + ((grp) * 4 + j_) * 32 + lane, ((dst)[j_ * 4] & ~1u) | H_BIT(l), (dst)[j_ * 4 + 1], (dst)[j_ * 4 + 2], (dst)[j_ * 4 + 3]); } \
    PINU(dst, 16); }
#define FRAG_PUT(src, slot) if (warp < 7) { _Pragma("unroll") for (int j_ = 0; j_ < 4; j_++) \
      sts128(sbase + (slot) * SLOT + 2048 + warp * 2048 + j_ * 512 + lane * 16, (src)[j_ * 4], (src)[j_ * 4 + 1], (src)[j_ * 4 + 2], (src)[j_ * 4 + 3]); }
#define FRAG_GET(dst, slot) { _Pragma("unroll") for (int j_ = 0; j_ < 4; j_++) \
      asm volatile("ld.shared.v4.u32 {%0, %1, %2, %3}, [%4];" : "=r"((dst)[j_ * 4]), "=r"((dst)[j_ * 4 + 1]), "=r"((dst)[j_ * 4 + 2]), "=r"((dst)[j_ * 4 + 3]) \
                   : "r"(sbase + (slot) * SLOT + warp * 2048 + j_ * 512 + lane * 16) : "memory"); }
#define RW(j) (((j) >> 1) * 4 + ((j) & 1))
template <int POS> __device__ __forceinline__ float exps16_(float* o, const float* p) {
  float s[4];
#pragma unroll
  for (int j = 0; j < 16; j++) { o[j] = ex2(POS ? p[RW(j)] : -p[RW(j)]); if (j < 4) s[j] = o[j]; else s[j & 3] += o[j]; }
  const float r = (s[0] + s[1]) + (s[2] + s[3]);
  return r + __shfl_xor_sync(0xffffffffu, r, 1);
}
template <int POS> __device__ __forceinline__ void exps16_fix(float* o, const float* p, float& sum) {
  if (__builtin_expect(__any_sync(0xffffffffu, !(sum > SUMLO && sum < SUMHI)), 0)) {
    float m = p[0], q[32];
#pragma unroll
    for (int j = 1; j < 16; j++) m = POS ? fmaxf(m, p[RW(j)]) : fminf(m, p[RW(j)]);
    const float x = __shfl_xor_sync(0xffffffffu, m, 1);
    m = POS ? fmaxf(m, x) : fminf(m, x);
#pragma unroll
    for (int j = 0; j < 16; j++) q[RW(j)] = p[RW(j)] - m;
    sum = exps16_<POS>(o, q);
  }
}
__device__ __forceinline__ void store16(const float* e, float sum, uint32_t dst, uint32_t dsw, int c0) {
  const float inv = rcp_fast(sum);
#pragma unroll
  for (int j = 0; j < 2; j++)
    sts128(dst + (((c0 + j) << 4) ^ dsw), pack_bf16(e[j * 8] * inv, e[j * 8 + 1] * inv), pack_bf16(e[j * 8 + 2] * inv, e[j * 8 + 3] * inv),
           pack_bf16(e[j * 8 + 4] * inv, e[j * 8 + 5] * inv), pack_bf16(e[j * 8 + 6] * inv, e[j * 8 + 7] * inv));
}
template <int POS> __device__ __forceinline__ void expp16(uint32_t* o, float* p) {
  {
#pragma unroll
    for (int r = 0; r < 4; r += 2) {
      float m = p[r];
#pragma unroll
      for (int j = 1; j < 8; j++) m = POS ? fmaxf(m, p[r + RW(j)]) : fminf(m, p[r + RW(j)]);
#pragma unroll
      for (int s = 1; s <= 2; s <<= 1) { const float x = __shfl_xor_sync(0xffffffffu, m, s); m = POS ? fmaxf(m, x) : fminf(m, x); }
#pragma unroll
      for (int j = 0; j < 8; j++) p[r + RW(j)] -= m;
    }
  }
#pragma unroll
  for (int j = 0; j < 8; j++) o[j] = pack_bf16(ex2(POS ? p[2 * j] : -p[2 * j]), ex2(POS ? p[2 * j + 1] : -p[2 * j + 1]));
}
__device__ __forceinline__ void scale32(float* o, const float* p, float c0, float c1) {
#pragma unroll
  for (int i = 0; i < 32; i++) asm volatile("mul.f32 %0, %1, %2;" : "=f"(o[i]) : "f"(p[i]), "f"((i & 2) ? c1 : c0));
}
__device__ __forceinline__ bool any_big(const float* p) {
  float m[4];
#pragma unroll
  for (int i = 0; i < 32; i++) m[i >> 3] = (i & 7) ? fmaf(p[i], p[i], m[i >> 3]) : p[i] * p[i];
  return __any_sync(0xffffffffu, !(fmaxf(fmaxf(m[0], m[1]), fmaxf(m[2], m[3])) < BIGLIM));
}
__device__ __forceinline__ void phiq_a(float* p, bool big) {
  if (__builtin_expect(!big, 1)) {
#pragma unroll
    for (int j = 0; j < 16; j++) p[j] = ex2(p[j]);
  }
}
__device__ __forceinline__ void phiq_b(uint32_t* o, float* p, bool big) {
  if (__builtin_expect(big, 0)) {
    expp16<0>(o, p); expp16<1>(o + 8, p);
  } else {
#pragma unroll
    for (int j = 0; j < 4; j++) {
      const float a = p[4 * j], b = p[4 * j + 1], c = p[4 * j + 2], d = p[4 * j + 3];
      const float ab = a * b, cd = c * d, r = rcp_fast(ab * cd), x = r * cd, y = r * ab;
      o[2 * j] = pack_bf16(x * b, x * a); o[2 * j + 1] = pack_bf16(y * d, y * c);
      o[8 + 2 * j] = pack_bf16(a, b); o[9 + 2 * j] = pack_bf16(c, d);
    }
  }
}
#define SCHED_FENCE() asm volatile("pmevent 0;" ::: "memory")

__global__ void __cluster_dims__(2, 1, 1) __launch_bounds__(384, 1)
mega_kernel(const __grid_constant__ CUtensorMap tm_x0, const __grid_constant__ CUtensorMap tm_xo, const __grid_constant__ CUtensorMap tm_os,
            const __grid_constant__ CUtensorMap tm_o, const __grid_constant__ CUtensorMap tm_wf,
            const __grid_constant__ CUtensorMap tm_wqA, const __grid_constant__ CUtensorMap tm_wqB,
            const __grid_constant__ CUtensorMap tm_woA, const __grid_constant__ CUtensorMap tm_woB,
            const __grid_constant__ CUtensorMap tm_phi, const Params prm) {
  extern __shared__ __align__(1024) uint8_t smem_raw[];
  const uint32_t sbase = smem_u32(smem_raw);
  const uint32_t bar_full = sbase + OFF_BAR;
  const uint32_t bar_done = bar_full + 384;
  const uint32_t bar_stat = bar_full + 768, bar_stat2 = bar_full + 776, bar_epi = bar_full + 784, bar_phi = bar_full + 936  , bar_halo = bar_full + 904  ;
  const uint32_t bar_xr = bar_full + 800, bar_lx = bar_full + 808, bar_stg = bar_full + 832;
  const uint32_t bar_chk = bar_full + 848;

  const int warp = __shfl_sync(0xffffffffu, threadIdx.x >> 5, 0), lane = threadIdx.x & 31;
  uint32_t rank;
  asm volatile("mov.u32 %0, %%cluster_ctarank;" : "=r"(rank));
  const int aux = (int)blockIdx.x - NMAIN, tp = (int)(blockIdx.x >> 1) - 4;
  const int gp = tp < 0 ? 0 : (tp < 32 ? tp & 7 : 1 + (tp - 32) % 7), me = tp < 0 ? tp + 8 : (tp < 32 ? tp >> 3 : 4 + (tp - 32) / 7);
  const int jj = me, cc = gp;
  const int cta = aux >= 0 ? -1 : (cc * 8 + jj) * 2 + (int)rank;
  const int mm = cc * 2 + (int)rank;

#define LOAD_EPOCH() const unsigned epoch = ld_relaxed(&g_flags.epoch.v), ep1 = epoch + 1; (void)epoch
  int budget = 1 << 22;

  if (cta >= 0) {
    if (warp >= 8 && warp < 8 + EARLY && elect_one()) {
      const int u = warp - 8;
      const uint32_t fb = bar_full + u * 8;
      mbar_init(fb, 1);
      asm volatile("fence.mbarrier_init.release.cluster;" ::: "memory");
      fence_proxy_async_smem();
      mbar_expect_tx(fb, u < 2 ? QST + SLOT : QST);
      if (u < 2) tma_load_2d(sbase + OFF_S + u * SLOT, &tm_x0, fb, jj * 128 + u * 64, mm * 128);
#pragma unroll
      for (int i = 0; i < 6; i++) tma_load_2d(sbase + u * QST + i * 4096, &tm_wqA, fb, jj * 128 + (u >> 1) * 64 + (i >> 1) * 1024, jj * 128 + (u & 1) * 64 + (i & 1) * 32);
      if (u == 0) PROFT(472);
    }
    __syncwarp();
    {
      const int tx = threadIdx.x;
      const __nv_bfloat16* pf = (tx < 128) ? prm.x0 + (size_t)(mm * 128 + tx) * D_MODEL + jj * 128
                                           : prm.wA_qkv + (size_t)(jj * 128 + (tx & 63)) * 3072 + ((tx - 128) >> 6) * 1024 + jj * 128 + rank * 64;
      if (tx < 320) { if (PF0) asm volatile("prefetch.global.L2 [%0];" :: "l"(pf)); }
      else if (tx == 320) prefetch_tmap(&tm_x0);
      else if (tx == 352) prefetch_tmap(&tm_wqA);
      else if (tx == 383) asm volatile("prefetch.global.L2 [%0];" :: "l"(&g_flags.epoch.v));
    }
    if (elect_one()) {
#pragma unroll
      for (int i = 0; i < 4; i++) {
        const int u = warp * 4 + i;
        if (u >= EARLY) mbar_init(bar_full + u * 8, ((u >= 4 && u < 11) || (u > 32 && u != 40)) ? 2 : 1); mbar_init(bar_done + u * 8, 16);
      }
      mbar_init(bar_stat + warp * 16, 0x111111181182ull >> (4 * warp) & 15);
      mbar_init(bar_stat + warp * 16 + 8, 0x111111121811ull >> (4 * warp) & 15);
      mbar_init(bar_chk + 112 + (warp & 7) * 8, 1);
      asm volatile("fence.mbarrier_init.release.cluster;" ::: "memory");
    }
    __syncthreads();
    asm volatile("barrier.cluster.arrive.relaxed.aligned;" ::: "memory");
  }

  if (cta < 0) {
    LOAD_EPOCH();
    const uint32_t buf = sbase + warp * SLOT, bar = sbase + OFF_BAR + warp * 16;
    const uint32_t lsw = (lane & 7) << 4, lhi = (lane >> 4) << 4, lrow = (lane & 15) * 128;
    const bool el = elect_one();
    if (el) {
      mbar_init(bar, 1); mbar_init(bar + 8, 1);
      asm volatile("fence.mbarrier_init.release.cluster;" ::: "memory");
    }
#pragma unroll 1
    for (int rd = 0; rd < (NLAYERS > 1 ? 5 : 2); rd++) {
      if (rd >= 2 && warp >= 8) break;
      const int tk = rd < 2 ? aux * 12 + warp : aux * 8 + warp;
      const int half = tk & 1;
      const int blk = rd < 2 ? (tk >> 1) * 2 + rd : (4 - rd) * 16 + (tk >> 1);
      const CUtensorMap* tm = rd < 2 ? &tm_wqA : (rd == 2 ? &tm_wqB : &tm_wf);
      const int j0 = (blk & 15) >> 1;
#define AUX_LOAD(n) { const uint32_t d_ = buf + ((n) & 1) * 8192, b_ = bar + ((n) & 1) * 8; const int r_ = kslice(j0, 2 * (n) + half) * 64; \
        mbar_expect_tx(b_, 8192); tma_load_2d(d_, tm, b_, blk * 64, r_); tma_load_2d(d_ + 4096, tm, b_, blk * 64, r_ + 32); }
      if (el) {
        if (rd == 3) { wait_flag(&g_flags.wfready[j0].v, ep1 * 16); fence_proxy_async_global(); }
        AUX_LOAD(0); AUX_LOAD(1);
      }
      __syncwarp();
      float cs[8][4];
#pragma unroll
      for (int i = 0; i < 8; i++) cs[i][0] = cs[i][1] = cs[i][2] = cs[i][3] = 0.f;
#pragma unroll 1
      for (int n = 0; n < 8; n++) {
        const uint32_t tb = buf + (n & 1) * 8192 + lrow;
        mbar_wait(bar + (n & 1) * 8, (n >> 1) & 1);
#pragma unroll
        for (int i = 0; i < 16; i++) {
          uint32_t b0, b1, b2, b3;
          ldsm_x4_t(tb + (i >> 2) * 2048 + (((i & 3) * 32 + lhi) ^ lsw), b0, b1, b2, b3);
          mma_bf16(cs[2 * (i & 3)], 0x3F803F80u, 0x3F803F80u, 0x3F803F80u, 0x3F803F80u, b0, b1);
          mma_bf16(cs[2 * (i & 3) + 1], 0x3F803F80u, 0x3F803F80u, 0x3F803F80u, 0x3F803F80u, b2, b3);
        }
        __syncwarp();
        if (el && n < 6) AUX_LOAD(n + 2);
        __syncwarp();
      }
      if (lane < 4) {
#pragma unroll
        for (int i = 0; i < 8; i++) st_b64(&g_colsum[rd >= 2][blk * 32 + i * 4 + lane][half], __float_as_uint(cs[i][0]), (__float_as_uint(cs[i][1]) & ~3u) | (ep1 & 3));
      }
      __syncwarp();
    }
  } else if (warp >= 8) {
    asm volatile("setmaxnreg.dec.sync.aligned.u32 40;");
    if (warp == 8) {
      const bool el = elect_one();
      cluster_wait();
      if (el) {
#pragma unroll 1
        for (int l = 0; l < NLAYERS; l++) {
          const uint32_t par = l & 1;
          const CUtensorMap* tqk = par ? &tm_wf : &tm_wqA;
          const CUtensorMap* tv = par ? &tm_wqB : &tm_wqA;
          const CUtensorMap* two = par ? &tm_woB : &tm_woA;
          if (l == 1) { LOAD_EPOCH(); wait_flag(&g_flags.wfready[jj].v, ep1 * 16); fence_proxy_async_global(); }
#pragma unroll 1
          for (int u = l ? 0 : EARLY; u < 32; u++) {
            if (u >= 4) mbar_wait_sl(bar_done + (u - 4) * 8, par);
            else if (l) mbar_wait_sl(bar_done + (43 + u + (u >> 1)) * 8, par ^ 1);
            else if (u == 1) __nanosleep(STAG1);
            else if (u == 2 && !W23) mbar_wait_sl(bar_full, 0);
            const uint32_t fb = bar_full + u * 8;
            const bool res = u < 4 ? (l || u >= 2) : (u < 11 || (u >= 18 && u < 22));
            mbar_expect_tx(fb, res ? QST : QST + SLOT);
            const int row = kslice(jj, u < 4 ? u & 1 : (u < 18 ? u - 2 : (u < 22 ? u - 6 : u - 20))) * 64 + (int)rank * 32;
            const int ps = u < 4 ? u >> 1 : (u >= 18), col = jj * 128 + ps * 64;
            const int c0 = par ? jj * 128 + (ps ? 0 : 1024) : col;
            const uint32_t dst = sbase + (u & 3) * QST + rank * 4096;
            tma_load_2d_mc(dst, tqk, fb, c0, row);
            tma_load_2d_mc(dst + 8192, tqk, fb, c0 + (par ? 64 : 1024), row);
            tma_load_2d_mc(dst + 16384, tv, fb, col + 2048, row);
            if (l == PRL && u >= PRU && u < PRU + 4) PROFT(473 + u - PRU);
          }
#pragma unroll 1
          for (int s = 0; s < 16; s++) {
            if (s < 5) { if (s != 2 && s != 4) mbar_wait_sl(bar_done + (28 + s) * 8, par); }
            else if (s != 14) mbar_wait_sl(bar_done + (27 + s - (s == 15)) * 8, par);
            const uint32_t fb = bar_full + (32 + s) * 8;
            mbar_expect_tx(fb, SLOT);
            tma_load_2d_mc(sbase + rank * 8192 + (uint32_t)((WO_BSLOT >> (4 * s)) & 15) * SLOT, two, fb, jj * 128 + (int)rank * 64, wslice(jj, s) * 64);
            const int ts = s + par;
            if (s >= 5 && ts < 8) {
              mbar_expect_tx(bar_chk - 8 + ts * 8, SLOT);
              tma_load_2d(sbase + (uint32_t)((WO_ASLOT(par) >> (4 * ts)) & 15) * SLOT, &tm_o, bar_chk - 8 + ts * 8, wslice(jj, ts) * 64, mm * 128);
            }
          }
        }
      }
      __syncwarp();
    } else if (warp == 9) {
      const bool el = elect_one();
      if (el) {
        if (!EARLY) { PROFT(472); tma_load_2d(sbase + OFF_S, &tm_x0, bar_full, jj * 128, mm * 128); }
        if (EARLY < 2) { __nanosleep(STAG1); tma_load_2d(sbase + OFF_S + SLOT, &tm_x0, bar_full + 8, jj * 128 + 64, mm * 128); }
      }
      __syncwarp();
      LOAD_EPOCH();
#pragma unroll 1
      for (int lp = 0; lp < 4 * NLAYERS; lp++) {
        const int l = lp >> 2, ph = lp & 3;
        if (ph == 3) continue;
        const uint32_t par = l & 1;
        const unsigned* pp = reinterpret_cast<const unsigned*>(g_obuf + (ph >> 1) * 64 + (size_t)(mm * 128 + (ph ? 0 : S_LEN) + (lane & 7) * 16 + (jj & 1) * 8) * D_MODEL +
                                                               (jj >> 1) * 16 + srcb(jj, lane >> 3) * 128);
        const CUtensorMap* tm = lp ? &tm_o : &tm_x0;
        const int row = mm * 128 + ((ph || !l) ? 0 : S_LEN);
        const uint32_t bit = ph ? O_BIT(l) : X_BIT(l - 1);
        const uint32_t slots = ph ? (uint32_t)(WO_ASLOT(par) >> (ph * 32 - 28)) : 0x8769876u;
        const unsigned long long fr = ph == 0 ? XPACE : ph == 1 ? (par ? 0x353535351Full : 0x35351F1Eull) : (par ? 0x27262524232232ull : 0x27262524233232ull);
        uint32_t no = (lp == 0 || (lp & 7) == 1) ? 0 : ~0u, v0 = 0, v1 = 0;
        if (lp || !AX) mbar_wait_sl(ph ? bar_done + ((uint32_t)fr & 63) * 8 : (l ? bar_done + 47 * 8 : bar_full), ph ? par : (l ? par ^ 1 : 0));
        if (el && ph) PROFT(324 + l * 16 + ph);
        __syncwarp();
        if (no) { v0 = ld_relaxed(pp); __nanosleep(POLLGAP); v1 = ld_relaxed(pp); }
#pragma unroll 1
        for (int i = 0; i < (ph == 1 ? 4 + par : 7); i++, no >>= 8) {
#pragma unroll 1
          for (int it = 0; (no & 0xFF) && it < (1 << 18); it++) {
            no &= __ballot_sync(0xffffffffu, (v0 ^ bit) & 1) >> (8 * i);
            if (no) v0 = ld_relaxed(pp);
            if (!(no & 0xFF)) break;
            no &= __ballot_sync(0xffffffffu, (v1 ^ bit) & 1) >> (8 * i);
            if (no) v1 = ld_relaxed(pp);
          }
          if (ph || i >= XP0) mbar_wait_sl(bar_done + ((uint32_t)(fr >> (8 * i)) & 63) * 8, par);
          if (el) {
            if (i == 0) PROFT(320 + l * 16 + ph);
            const uint32_t cb = bar_chk + (ph >> 1) * 112 + i * 8;
            mbar_expect_tx(cb, SLOT);
            tma_load_2d(sbase + ((slots >> (4 * i)) & 15) * SLOT, tm, cb, srcb(jj, i) * 128 + (ph >> 1) * 64, row);
          }
          __syncwarp();
        }
        if (ph == 0 && el) {
          if (l) { wait_flag(&g_flags.xready[l][mm].v, ep1 * 8); fence_proxy_async_global(); }
#pragma unroll 1
          for (int u = 11; u < 34; u++) {
            if (u == 18) u = 22;
            mbar_wait_sl(bar_done + (u - 4) * 8, par);
            if (u == 32) mbar_expect_tx(bar_xr, 2 * SLOT);
            tma_load_2d(sbase + OFF_RA + (u & 3) * SLOT, tm, u < 32 ? bar_full + u * 8 : bar_xr, kslice(jj, u < 18 ? u - 2 : (u < 32 ? u - 20 : u - 32)) * 64, row);
          }
        }
        __syncwarp();
      }
      if (el && atomicAdd(&g_flags.done.v, 1) == ep1 * NMAIN - 1) asm volatile("st.relaxed.gpu.global.u32 [%0], %1;" :: "l"(&g_flags.epoch.v), "r"(ep1) : "memory");
      __syncwarp();
      cluster_wait();
    } else {
      const int hw = warp - 10;
      LOAD_EPOCH();
      const bool el = elect_one();
      cluster_wait();
      if (hw == 0) {
        mbar_wait_sl(bar_full + 8, 0);
        if (lane < 7) prefetch_tmap(lane == 0 ? &tm_os : lane == 1 ? &tm_o : lane == 2 ? &tm_wf : lane == 3 ? &tm_wqB : lane == 4 ? &tm_woA : lane == 5 ? &tm_woB : &tm_phi);
#pragma unroll 1
        for (int i = 0; i < (NLAYERS > 1 ? 9 : 0); i++) {
          if (i == 0 || i == 5) mbar_wait_sl(bar_done + (i >> 1) * 12, 0);
          if (el) {
            if (i == 0) { mbar_expect_tx(bar_phi, 2 * SLOT + 8192); tma_load_2d(sbase + OFF_PHI, &tm_phi, bar_phi, 0, jj * 128); }
            else tma_load_2d(sbase + (i > 4 ? 10 : 12) * SLOT - 4096 + i * 4096, &tm_wqB, bar_phi, (i > 4 ? 896 : 0) + jj * 128 + ((i - 1) >> 1) * 64, mm * 64 + (~i & 1) * 32);
          }
          __syncwarp();
          __nanosleep(PFGAP);
        }
      } else {
#pragma unroll 1
        for (int b = 0; b < 2; b++) {
          float4* z = reinterpret_cast<float4*>(g_kv[b] + (jj * 4) * KVH + mm * (4 * KVH / 16)) + lane;
#pragma unroll
          for (int i = 0; i < 6; i++) z[i * 32] = make_float4(0.f, 0.f, 0.f, 0.f);
        }
#pragma unroll 1
        for (int i = 0; i < 16; i++) {
          const int b = i >> 2;
          const uint32_t v = (b == 0 ? O_BIT(0) : b == 1 ? X_BIT(0) : H_BIT(0)) + 1;
          uint4* p = b < 2 ? reinterpret_cast<uint4*>(g_obuf + (size_t)(b * S_LEN + mm * 128 + (i & 3) * 32 + (lane >> 3) * 8) * D_MODEL + jj * 128 + (b ? 0 : 64)) + (lane & 7)
                           : g_halo + (size_t)(mm * 8 + jj) * 512 + i * 32 + lane;
          *p = make_uint4(v, v, v, v);
        }
        fence_proxy_async_global();
      }
      __syncwarp();
      uint32_t chkp = 0;
#pragma unroll 1
      for (int lp = 0; lp < 4 * NLAYERS; lp++) {
        const int l = lp >> 2, ph = (lp & 3) == 2 ? 2 - hw : (lp & 3);
        const uint32_t par = l & 1;
        int lane; asm volatile("mov.u32 %0, %%laneid;" : "=r"(lane));
        if ((lp & 3) == 2 || (hw && ph == 0)) {
          const uint32_t bit = ph ? O_BIT(l) : X_BIT(l - 1);
          uint32_t slots = ph ? (uint32_t)(WO_ASLOT(par) >> (ph * 32 - 28)) : 0x8769876u;
          const uint32_t a0 = sbase + (lane & 7) * 132 + (lane >> 3) * 32;
#pragma unroll 1
          for (int c = 0; c < 7; c++, slots >>= 4) {
            const uint32_t cb = bar_chk + 112 - hw * 112 + c * 8;
#pragma unroll 1
            for (int it = 0; it < (1 << 12); it++) {
              mbar_wait_sl(cb, (chkp >> c) & 1);
              chkp ^= 1u << c;
              if (el && c == 0) PROFT(ph == 1 ? 480 + l * 2 : 488 + l * 2 + (ph >> 1));
              if (lp == 0) break;
              uint32_t bad;
              asm volatile("{\n.reg .b32 w<16>;\n"
                           "ld.shared.u32 w0, [%1 + 0];\n"
                           "ld.shared.u32 w1, [%1 + 1024];\n"
                           "ld.shared.u32 w2, [%1 + 2048];\n"
                           "ld.shared.u32 w3, [%1 + 3072];\n"
                           "ld.shared.u32 w4, [%1 + 4096];\n"
                           "ld.shared.u32 w5, [%1 + 5120];\n"
                           "ld.shared.u32 w6, [%1 + 6144];\n"
                           "ld.shared.u32 w7, [%1 + 7168];\n"
                           "ld.shared.u32 w8, [%1 + 8192];\n"
                           "ld.shared.u32 w9, [%1 + 9216];\n"
                           "ld.shared.u32 w10, [%1 + 10240];\n"
                           "ld.shared.u32 w11, [%1 + 11264];\n"
                           "ld.shared.u32 w12, [%1 + 12288];\n"
                           "ld.shared.u32 w13, [%1 + 13312];\n"
                           "ld.shared.u32 w14, [%1 + 14336];\n"
                           "ld.shared.u32 w15, [%1 + 15360];\n"
                           "lop3.b32 w0, w0, w1, %2, 0x7E;\n"
                           "lop3.b32 w2, w2, w3, %2, 0x7E;\n"
                           "lop3.b32 w4, w4, w5, %2, 0x7E;\n"
                           "lop3.b32 w6, w6, w7, %2, 0x7E;\n"
                           "lop3.b32 w8, w8, w9, %2, 0x7E;\n"
                           "lop3.b32 w10, w10, w11, %2, 0x7E;\n"
                           "lop3.b32 w12, w12, w13, %2, 0x7E;\n"
                           "lop3.b32 w14, w14, w15, %2, 0x7E;\n"
                           "lop3.b32 w0, w0, w2, w4, 0xFE;\nlop3.b32 w6, w6, w8, w10, 0xFE;\nlop3.b32 w0, w0, w12, w14, 0xFE;\nlop3.b32 %0, w0, w6, 1, 0xA8;\n}\n"
                           : "=r"(bad) : "r"(a0 + (slots & 15) * SLOT), "r"(bit) : "memory");
              if (__all_sync(0xffffffffu, bad == 0)) break;
              if (el) {
                fence_proxy_async_smem();
                mbar_expect_tx(cb, SLOT);
                tma_load_2d(sbase + (slots & 15) * SLOT, &tm_o, cb, srcb(jj, c) * 128 + (ph >> 1) * 64, mm * 128 + (ph ? 0 : S_LEN));
                RETRY_COUNT();
              }
              __syncwarp();
            }
            if (el) { mbar_arrive_local(bar_full + (c + (ph ? 25 + ph * 8 : 4)) * 8); if (lp == PRL * 4 && c == 0) PROFT(477); }
            __syncwarp();
          }
          if (ph) continue;
#pragma unroll 1
          for (int hp = 0; hp < 2; hp++) {
            const uint4* src = reinterpret_cast<const uint4*>(g_colsum[par][jj * 64 + hp * 32 + lane]);
            uint32_t bad;
            int it = 0;
            float c[6];
            do {
              bad = 0;
#pragma unroll
              for (int p = 0; p < 3; p++) {
                const uint4 v = ld_ll(src + ((par && p < 2) ? (hp ? -32 : 512) + p * 32 : p * 512));
                bad |= (v.y ^ ep1) | (v.w ^ ep1);
                c[2 * p] = __uint_as_float(v.x) + __uint_as_float(v.z); c[2 * p + 1] = __uint_as_float(v.y) + __uint_as_float(v.w);
              }
              bad &= 3;
              if (bad) __nanosleep(300);
            } while (bad && ++it < (1 << 16));
#pragma unroll
            for (int p = 0; p < 6; p++) {
              uint32_t h, m, lo;
              split3(c[p], h, m, lo);
              sts128(sbase + OFF_LNB + hp * 4096 + (p >> 1) * 1024 + lane * 32 + (p & 1) * 16, h | (m << 16), h | (lo << 16), h | (m << 16), lo | (m << 16));
            }
            fence_proxy_async_smem();
            __syncwarp();
            if (el) { mbar_arrive_local(hp ? bar_stat2 : bar_stat); if (hp == 0) PROFT(324 + l * 16); }
            __syncwarp();
          }
          continue;
        } else if (ph == 0) {
          mbar_wait_sl(bar_done + 24, par);
          const uint4* sp = reinterpret_cast<const uint4*>(g_stats + (size_t)(mm * 128) * 8) + lane;
#pragma unroll 1
          for (int hf = 0; hf < 4; hf++) {
            uint4 v[4];
            uint32_t bad;
            int it = 0;
            do {
              bad = 0;
#pragma unroll
              for (int i = 0; i < 4; i++) { v[i] = ld_ll(sp + (hf * 4 + i) * 32); bad |= (v[i].y ^ STAT_TAG(l)) | (v[i].w ^ STAT_TAG(l)); }
              bad &= 3;
              if (bad) __nanosleep(200);
            } while (bad && ++it < (1 << 16));
            __syncwarp();
            float mean = 0.f, m2 = 0.f;
#pragma unroll
            for (int i = 0; i < 4; i++) {
              float a = __uint_as_float(v[i].x) + __uint_as_float(v[i].z);
              a += __shfl_xor_sync(0xffffffffu, a, 1); a += __shfl_xor_sync(0xffffffffu, a, 2);
              a *= 0.125f;
              const float e0 = __uint_as_float(v[i].x) - a, e1 = __uint_as_float(v[i].z) - a;
              float q = fmaf(fmaf(e0, e0, e1 * e1), 128.f, __uint_as_float(v[i].y) + __uint_as_float(v[i].w));
              q += __shfl_xor_sync(0xffffffffu, q, 1); q += __shfl_xor_sync(0xffffffffu, q, 2);
              if ((lane & 3) == i) { mean = a; m2 = q; }
            }
            const uint32_t row = hf * 32 + (lane & 3) * 8 + (lane >> 2);
            uint32_t h, m, lo;
            split3(-0.5f * mean, h, m, lo);
            sts128(sbase + OFF_LNA + row * 16, h | (h << 16), m | (h << 16), lo | (m << 16), m | (lo << 16));
            sts32f(sbase + OFF_ST + row * 4, rsqrtf(m2 * (1.f / 1024.f) + 1e-5f));
          }
          fence_proxy_async_smem();
          __syncwarp();
          if (el) { mbar_arrive_local(bar_stat); PROFT(323 + l * 16); }
          __syncwarp();
#pragma unroll 1
          for (int i = 0; i < 8 - 4 * l; i++) {
            asm volatile("prefetch.global.L2 [%0];" :: "l"(i < 4 ? (l ? prm.wB_o : prm.wA_o) + (size_t)cta * 8192 + i * 2048 + lane * 64
                                                                 : prm.wB_qkv + (size_t)(cta * 8 + (i - 4) * 2 + (lane >> 4)) * 3072 + 2048 + (lane & 15) * 64));
            __nanosleep(PFGAP);
          }
          continue;
        }
        if (ph == 1) {
          if (par) continue;
#pragma unroll 1
          for (int i = 0; i < 2; i++) {
            if (i && lp + hw == 1 && NLAYERS > 1) {
#pragma unroll 1
              for (int c = 0; c < 8; c++) {
                if (!(c & 3)) asm volatile("bar.sync %0, 288;" :: "r"(BAR_WF + (c >> 2)) : "memory");
                if (el) {
                  tma_store_2d(&tm_wf, sbase + 11 * SLOT + c * 4096, (c < 4 ? 1024 : -128) + jj * 128 + (c >> 1) * 64, mm * 64 + (c & 1) * 32);
                  if ((c & 3) == 3) {
                    asm volatile("cp.async.bulk.commit_group;\ncp.async.bulk.wait_group.read 0;" ::: "memory");
                    mbar_arrive_local(bar_phi + (c >> 2) * 8);
                  } else __nanosleep(WFGAP);
                }
                __syncwarp();
              }
              if (el) { bulk_commit_wait(); signal_release(&g_flags.wfready[jj].v); PROFT(335); }
              __syncwarp();
            }
            mbar_wait_sl(bar_done + (i ? HW1 : (hw ? 19 : HW0)) * 8, 0);
            if (lp + hw == 2 && NLAYERS > 1) mbar_wait_sl(bar_phi, 1);
            const uint4* src = g_halo + (size_t)(mm * 8 + jj - 8) * 512 + i * 256 + hw * 128 + lane;
            uint4 v[4];
            int it = 0;
            bool ok;
            do {
#pragma unroll
              for (int j = 0; j < 4; j++) v[j] = mm ? ld_b128(src + j * 32) : make_uint4(H_BIT(l), 0, 0, 0);
              ok = __all_sync(0xffffffffu, (((v[0].x ^ H_BIT(l)) | (v[1].x ^ H_BIT(l)) | (v[2].x ^ H_BIT(l)) | (v[3].x ^ H_BIT(l))) & 1) == 0);
            } while (!ok && ++it < (1 << 16));
#pragma unroll
            for (int j = 0; j < 4; j++) sts128(sbase + OFF_S + hw * SLOT + j * 512 + lane * 16, v[j].x, v[j].y, v[j].z, v[j].w);
            __syncwarp();
            if (el) { mbar_arrive_local(bar_halo + hw * 8); PROFT(331 + l * 16 + i * 2 + hw); }
            __syncwarp();
          }
        } else if (hw == 0 && l < NLAYERS - 1) {
          bar_sync<BAR_X1, 288>();
          if (el) {
            PROFT(328 + l * 16);
            mbar_wait_sl(bar_full + XD * 8, par ^ 1);
            tma_store_2d(&tm_o, sbase + 11 * SLOT, jj * 128 + 64, mm * 128 + S_LEN);
            bulk_commit_wait();
            signal_release(&g_flags.xready[l + 1][mm].v);
            PROFT(330 + l * 16);
          }
          __syncwarp();
        }
      }
    }
    cluster_sync();
  } else {
    asm volatile("setmaxnreg.inc.sync.aligned.u32 232;");
    LOAD_EPOCH();
    const int wg = warp >> 2;
    const int r0 = warp * 16;
    const uint32_t pK = sbase + OFF_S, pV = sbase + OFF_S + SLOT;
#define PMASKS(on, bit) const uint32_t pm0 = ((on) && t == (g & 3) && (g >> 2) == (g & 1)), pm1 = ((on) && t == (g & 3) && (g >> 2) != (g & 1)), pbit = (bit)
#define PBIT0(w) (((w) & ~pm0) | (pbit & pm0))
#define PBIT1(w) (((w) & ~pm1) | (pbit & pm1))
#define LANE_CONSTS() \
    int lane; asm volatile("mov.u32 %0, %%laneid;" : "=r"(lane)); \
    const int g = lane >> 2, t = lane & 3; \
    const uint32_t srowoff = (r0 + (lane & 15)) * 128, lsw = (lane & 7) << 4, lhi = (lane >> 4) << 4, lsw2 = (lane & 6) << 3; \
    (void)g; (void)t; (void)srowoff; (void)lsw; (void)lhi; (void)lsw2;
    uint32_t stgp = 0, peer;
    asm volatile("mapa.shared::cluster.u32 %0, %1, %2;" : "=r"(peer) : "r"(sbase), "r"(rank ^ 1));
    peer -= sbase;
    const uint32_t dA0 = (((sbase & 0x3FFFF) + wg * 8192) >> 4) | 0x10000u, dB0 = ((sbase & 0x3FFFF) >> 4) | 0x2000000u;
    cluster_wait();
#define DESC(lo, hi) ((uint64_t)(uint32_t)(lo) | ((uint64_t)(hi) << 32))
#define STG_ARRIVE() { __syncwarp(); if (elect_one()) mbar_arrive_local(bar_stg); }
#define STG_WAIT() { mbar_wait(bar_stg, stgp); stgp ^= 1; }
#define PROFS() do {} while (0)
#define REL(addr) { if (elect_one()) { mbar_arrive_local(addr); asm volatile("mbarrier.arrive.shared::cluster.b64 _, [%0];" :: "r"((addr) + peer) : "memory"); } }
#define QSTEP(ACC, DA, SC, PRE) { \
      const uint32_t da = (DA), db = dB0 + (ub & 0x18) * (QST >> 7); \
      mbar_wait(ub, par); \
      PRE; \
      wgmma_fence(); \
      wgmma4_n192<SC>(ACC, da, db); \
      wgmma_commit(); PROFS(); }
#define QREL() { wgmma_wait<1>(); REL(ub + 376); ub += 8; }
#define RA_CUR (dA0 + (OFF_RA >> 4) + (ub & 0x18) * (SLOT >> 7))
#define PUMP1() { QSTEP(S1, RA_CUR, 1, {}); QREL(); }
#define PUMP0() { PUMP1(); SCHED_FENCE(); }
#define PUMP() if (h == 0) PUMP1()
#define WSTEP() { \
      const uint32_t s4 = (ub - bar_full - 256) >> 1; \
      const uint32_t da = dA0 + (((uint32_t)(WO_ASLOT(par) >> s4) & 15) << 10), db = dB0 + (((uint32_t)(WO_BSLOT >> s4) & 15) << 10); \
      mbar_wait(ub, par); \
      wgmma_fence(); \
      wgmma4_n128<1>(S1, da, db); \
      wgmma_commit(); PROFS(); \
      wgmma_wait<1>(); \
      if (s4) REL(ub + 376); \
      ub += 8; }
#define PUMPS(n) { _Pragma("unroll 1") for (int i_ = 0; i_ < (n); i_++) PUMP1(); }
#define SITE(n) { if ((BMASK >> (n)) & 1) PUMP1(); SCHED_FENCE(); }
#define LNSTEP(ACC, hh) { wgmma_fence(); wgmma_n192<1, 0>(ACC, make_desc(sbase + OFF_LNA + wg * 1024, 0, 128) ^ (1ull << 62), make_desc(sbase + OFF_LNB + (hh) * 4096, 0, 128) ^ (1ull << 62)); }
#define WARP_STORE(tm, tile, col, row) { fence_proxy_async_smem(); __syncwarp(); \
      if (elect_one()) { tma_store_2d(tm, (tile) + r0 * 128, col, (row) + r0); asm volatile("cp.async.bulk.commit_group;" ::: "memory"); } __syncwarp(); }
#define PUBLISH_O() WARP_STORE(&tm_os, pO, jj * 128 + h * 64, mm * 128)
#define TILE_CONSTS(base, on, bit) \
      uint32_t ta[6]; \
      { PMASKS(on, bit); (void)pbit; ta[4] = pm0; ta[5] = pm1; } \
      _Pragma("unroll") for (int j = 0; j < 4; j++) ta[j] = (base) + srowoff + ((((uint32_t)j << 5) + lhi) ^ lsw); \
      PINU(ta, 6); SCHED_FENCE(); \
      const uint32_t pm0 = ta[4], pm1 = ta[5], pbit = (bit)
#define X_OUT(pc) { \
      _Pragma("unroll") for (int j = (pc) * 4; j < (pc) * 4 + 4; j++) \
        stsm_x4(ta[j & 3] + (pc) * SLOT, \
                PBIT0(pack_bf16(S1[j * 8 + 0], S1[j * 8 + 1])), PBIT0(pack_bf16(S1[j * 8 + 2], S1[j * 8 + 3])), \
                PBIT1(pack_bf16(S1[j * 8 + 4], S1[j * 8 + 5])), PBIT1(pack_bf16(S1[j * 8 + 6], S1[j * 8 + 7]))); }
#define REST_P1(SKEW) { \
      mbar_wait(bar_stat2, par); \
      LNSTEP(S1, 1); \
      _Pragma("unroll 1") while (ub < bar_full + 256) { \
        if (ub == bar_full + 256 - 8 * (SKEW) && wg == 0) bar_sync<BAR_SKEW, 256>(); \
        QSTEP(S1, RA_CUR, 1, {}); \
        if (ub == bar_full + 248 && wg == 1) bar_arrive<BAR_SKEW, 256>(); \
        QREL(); \
      } \
      mbar_wait(bar_done + (31 - (SKEW)) * 8, par);        \
      wgmma_wait<0>(); \
      ACC_FENCE(S1, 96); \
      REL(bar_done + 31 * 8); \
      PROF(13); }
#define FOLD(tile, rd) { \
          LANE_CONSTS(); \
          float d[32]; \
          ACC_DEF(d, 32); \
          mbar_wait(bar_phi, 0); \
          wgmma_fence(); \
          _Pragma("unroll") for (int i = 0; i < 2; i++) { \
            const uint64_t da = make_desc((tile) + wg * 8192 + i * 64, 16, 1024); \
            const uint64_t db = make_desc(sbase + OFF_PHI + wg * 4096 + i * 2048, 16, 512) ^ (3ull << 62); \
            wgmma_n32<0>(d + i * 16, da, db); wgmma_n32<1>(d + i * 16, da + 2, db + 64); \
          } \
          wgmma_commit(); \
          PUMP0(); \
          ACC_FENCE(d, 32); \
          bar_wg(wg); \
          _Pragma("unroll") for (int i = 0; i < 4; i++) { \
            const float* x = d + (i & 1) * 8 + (i >> 1) * 2; \
            if (rd) sts128((tile) + wg * 8192 + ((warp & 3) * 16 + (i >> 1) * 8 + g) * 128 + (((2 * t + (i & 1)) ^ g) << 4), \
                           pack_bf16(x[0], x[1]), pack_bf16(x[4], x[5]), pack_bf16(x[16], x[17]), pack_bf16(x[20], x[21])); \
            else stsm_x4((tile) + srowoff + ((((uint32_t)i << 5) + lhi) ^ lsw), pack_bf16(d[i * 8], d[i * 8 + 1]), pack_bf16(d[i * 8 + 2], d[i * 8 + 3]), \
                         pack_bf16(d[i * 8 + 4], d[i * 8 + 5]), pack_bf16(d[i * 8 + 6], d[i * 8 + 7])); \
          } \
          }
#define LOAD_X0(base) \
      _Pragma("unroll") for (int j = 0; j < 8; j++) { \
        uint32_t x0, x1, x2, x3; \
        ldsm_x4((base) + (j >> 2) * SLOT + srowoff + ((((uint32_t)(j & 3) << 5) + lhi) ^ lsw), x0, x1, x2, x3); \
        S1[j * 8 + 0] = bf_lo(x0); S1[j * 8 + 1] = bf_hi(x0); S1[j * 8 + 2] = bf_lo(x1); S1[j * 8 + 3] = bf_hi(x1); \
        S1[j * 8 + 4] = bf_lo(x2); S1[j * 8 + 5] = bf_hi(x2); S1[j * 8 + 6] = bf_lo(x3); S1[j * 8 + 7] = bf_hi(x3); \
      }
#define LOAD_X() { \
      wgmma_wait<0>(); \
      mbar_wait(bar_xr, par); \
      LOAD_X0(sbase + OFF_RA); \
      ACC_FENCE(S1, 64); \
      __syncwarp(); if (elect_one()) mbar_arrive_local(bar_lx); }

    float S1[96];
#pragma unroll
    for (int i = 0; i < 64; i++) S1[i] = 0.f;
#pragma unroll 1
    for (int l = 0; l < NLAYERS; l++) {
      const uint32_t par = l & 1;
      bar_wg(wg);
      PROF(0);
      uint32_t ub = bar_full;
      float S0[96];
      {
        LANE_CONSTS();
        ACC_DEF(S0, 96);
        QSTEP(S0, dA0 + (OFF_S >> 4), 0, {});
        ub += 8;
        PROF(1);
        if (l == 0) { mbar_wait(ub, 0); LOAD_X0(pK); }
        else { uint32_t ta[4]; for (int j = 0; j < 4; j++) ta[j] = pK + srowoff + ((((uint32_t)j << 5) + lhi) ^ lsw); PMASKS(false, 0); X_OUT(1); fence_proxy_async_smem(); }
        SCHED_FENCE();
        {
          float a0 = S1[0], a1 = S1[2], b0 = S1[1], b1 = S1[3];
#pragma unroll
          for (int i = 4; i < 64; i += 4) { a0 += S1[i]; b0 += S1[i + 1]; a1 += S1[i + 2]; b1 += S1[i + 3]; }
          a0 += b0; a1 += b1;
          a0 += __shfl_xor_sync(0xffffffffu, a0, 1); a1 += __shfl_xor_sync(0xffffffffu, a1, 1);
          a0 += __shfl_xor_sync(0xffffffffu, a0, 2); a1 += __shfl_xor_sync(0xffffffffu, a1, 2);
          a0 *= (1.f / 128.f); a1 *= (1.f / 128.f);
          asm volatile("" : "+f"(a0), "+f"(a1));
          bar_wg(wg);
          QSTEP(S0, dA0 + ((OFF_S + SLOT) >> 4), 1, wgmma_wait<0>());
          REL(ub + 376); ub += 8;
          SCHED_FENCE();
          float q0 = 0.f, q1 = 0.f;
          b0 = 0.f; b1 = 0.f;
#pragma unroll
          for (int i = 0; i < 64; i += 4) {
            const float d0 = S1[i] - a0, d1 = S1[i + 1] - a0, d2 = S1[i + 2] - a1, d3 = S1[i + 3] - a1;
            q0 = fmaf(d0, d0, q0); b0 = fmaf(d1, d1, b0); q1 = fmaf(d2, d2, q1); b1 = fmaf(d3, d3, b1);
          }
          q0 += b0; q1 += b1;
          q0 += __shfl_xor_sync(0xffffffffu, q0, 1); q1 += __shfl_xor_sync(0xffffffffu, q1, 1);
          q0 += __shfl_xor_sync(0xffffffffu, q0, 2); q1 += __shfl_xor_sync(0xffffffffu, q1, 2);
          if (t < 2) st_b64(g_stats + (size_t)(mm * 128 + r0 + g + t * 8) * 8 + jj, __float_as_uint(t ? a1 : a0), (__float_as_uint(t ? q1 : q0) & ~3u) | STAT_TAG(l));
        }
        if (l) { asm volatile("cp.async.bulk.wait_group 0;" ::: "memory"); bar_arrive<BAR_X1, 288>(); }
        ACC_DEF(S1, 96);
        QSTEP(S1, dA0 + (OFF_S >> 4), 0, {});
        QREL();
        QSTEP(S1, dA0 + ((OFF_S + SLOT) >> 4), 1, {});
        QREL();
#pragma unroll 1
        for (int i = 0; i < 14; i++) {
          QSTEP(S0, RA_CUR, 1, {});
          if (i == 0) PROF(2);
          QREL();
        }
      }
      LANE_CONSTS();
      mbar_wait(bar_stat, par);
      LNSTEP(S0, 0);
      wgmma_commit();
      const float rs0 = lds32f(sbase + OFF_ST + (r0 + g) * 4), rs1 = lds32f(sbase + OFF_ST + (r0 + g + 8) * 4);
      PUMP0();
      ACC_FENCE(S0, 96);
      PROF(3);
      if (!par) {
        constexpr uint32_t par = 0;
        uint32_t qa[16];
        uint32_t kf[32], vf[32];
#define DRAIN_A(ACC, hp, PMP) { \
          LANE_CONSTS(); \
          FRAG(kf + 16, ACC + 32, 0, (hp) * 2); \
          PMP; \
          FRAG(vf + 16, ACC + 64, 1, (hp) * 2 + 1); \
          _Pragma("unroll") for (int i_ = 0; i_ < 16; i_++) qa[i_] = pack_bf16(ACC[2 * i_], ACC[2 * i_ + 1]); \
          PINU(qa, 16); }
        DRAIN_A(S0, 0, PUMP0());
        if (l == 0 && NLAYERS > 1) {
#pragma unroll 1
          for (int rd = 1; rd >= 0; rd--) {
            FOLD(sbase + (12 - rd) * SLOT, rd);
            fence_proxy_async_smem();
            asm volatile("bar.arrive %0, 288;" :: "r"(BAR_WF + 1 - rd) : "memory");
          }
        }
        PUMPS(FPUMP);
        if (l == 0 && NLAYERS > 1) mbar_wait(bar_phi, 1);
#pragma unroll 1
        for (int h = 0; h < 2; h++) {
          const uint32_t pO = sbase + (h ? 3 : 12) * SLOT;
          PROF(4 + h * 12);
          LANE_CONSTS();
          FRAG_PUT(kf + 16, 10); FRAG_PUT(vf + 16, 11);
          STG_ARRIVE();
          if (h) { LOAD_X(); if (AW0) WSTEP(); } else PUMPS(HPUMP2);
          const bool e = g & 1, hb = (2 * t + (g & 1)) <= g;
          uint32_t sel[3] = {e ? 0x1044u : 0x4410u, hb ? 0x4444u : (e ? 0x3244u : 0x4432u), hb ? (e ? 0x3244u : 0x4432u) : 0x4444u};
          PINU(sel, 3);
          TILE_CONSTS(pO, true, O_BIT(l));
          const uint32_t selA = sel[0], selL = sel[1], selH = sel[2];
          STG_WAIT();
          if (warp == 0) mbar_wait(bar_halo, h);
          FRAG_GET(kf, 10);
          PROF(5 + h * 12);
          float s[2][4][4];
#pragma unroll
          for (int ks = 0; ks < 2; ks++)
#pragma unroll
            for (int i = 0; i < 8; i++) {
              const int hh = (i >> 1) & 1, jb = (i & 1) + (~i >> 1 & 2);
              const uint32_t* b = kf + (jb >> 1) * 16 + hh * 8 + ks * 4 + (jb & 1) * 2;
              if (ks) mma_bf16(s[hh][jb], qa[hh * 8 + 4], qa[hh * 8 + 5], qa[hh * 8 + 6], qa[hh * 8 + 7], b[0], b[1]);
              else mma_bf16_z(s[hh][jb], qa[hh * 8], qa[hh * 8 + 1], qa[hh * 8 + 2], qa[hh * 8 + 3], b[0], b[1]);
            }
          PUMP();
          PROF(6 + h * 12);
          float va[2][2], vb[2][2], mx[2][2];
#pragma unroll
          for (int hh = 0; hh < 2; hh++) {
            va[hh][0] = e ? s[hh][1][1] : s[hh][1][0];
            vb[hh][0] = hb ? (e ? s[hh][2][1] : s[hh][2][0]) : (e ? s[hh][0][1] : s[hh][0][0]);
            va[hh][1] = e ? s[hh][2][3] : s[hh][2][2];
            vb[hh][1] = hb ? (e ? s[hh][3][3] : s[hh][3][2]) : (e ? s[hh][1][3] : s[hh][1][2]);
          }
          if (warp == 0 && mm == 0) {
#pragma unroll
            for (int hh = 0; hh < 2; hh++) { va[hh][0] = -INFINITY; if (!hb) { vb[hh][0] = -INFINITY; vb[hh][1] = -INFINITY; } }
          }
#pragma unroll
          for (int i = 0; i < 4; i++) mx[i >> 1][i & 1] = fmaxf(va[i >> 1][i & 1], vb[i >> 1][i & 1]);
#pragma unroll
          for (int o = 1; o <= 2; o <<= 1)
#pragma unroll
            for (int i = 0; i < 4; i++) mx[i >> 1][i & 1] = fmaxf(mx[i >> 1][i & 1], __shfl_xor_sync(0xffffffffu, mx[i >> 1][i & 1], o));
          const float sc0 = rs0 * (0.17677669529663687f * LOG2E), sc1 = rs1 * (0.17677669529663687f * LOG2E);
#pragma unroll
          for (int i = 0; i < 4; i++) {
            const float sc = (i & 1) ? sc1 : sc0, m = mx[i >> 1][i & 1];
            va[i >> 1][i & 1] = ex2((va[i >> 1][i & 1] - m) * sc); vb[i >> 1][i & 1] = ex2((vb[i >> 1][i & 1] - m) * sc);
            mx[i >> 1][i & 1] = va[i >> 1][i & 1] + vb[i >> 1][i & 1];
          }
          if (h == 0 && ASITE) { PIN(&va[0][0], 4); PIN(&vb[0][0], 4); PIN(&mx[0][0], 4); PUMP1(); }
          if (warp == 0) mbar_wait(bar_halo + 8, h);
          FRAG_GET(vf, 11);
#pragma unroll
          for (int o = 1; o <= 2; o <<= 1)
#pragma unroll
            for (int i = 0; i < 4; i++) mx[i >> 1][i & 1] += __shfl_xor_sync(0xffffffffu, mx[i >> 1][i & 1], o);
          float o[2][4][4];
          uint32_t pa[2][8];
#pragma unroll
          for (int hh = 0; hh < 2; hh++) {
            const float i0 = rcp_fast(mx[hh][0]), i1 = rcp_fast(mx[hh][1]);
            const uint32_t w0 = pack_bf16(va[hh][0] * i0, vb[hh][0] * i0), w1 = pack_bf16(va[hh][1] * i1, vb[hh][1] * i1);
            pa[hh][0] = __byte_perm(w0, 0, selL); pa[hh][2] = __byte_perm(w0, 0, selA); pa[hh][3] = __byte_perm(w1, 0, selL);
            pa[hh][4] = __byte_perm(w0, 0, selH); pa[hh][5] = __byte_perm(w1, 0, selA); pa[hh][7] = __byte_perm(w1, 0, selH);
            pa[hh][1] = pa[hh][0] & pa[hh][4]; pa[hh][6] = pa[hh][3] & pa[hh][7];
          }
          PROF(7 + h * 12);
#pragma unroll
          for (int i = 0; i < 8; i++) mma_bf16_z(o[i >> 2][i & 3], pa[i >> 2][4], pa[i >> 2][5], pa[i >> 2][6], pa[i >> 2][7], vf[16 + 2 * i], vf[17 + 2 * i]);
#pragma unroll
          for (int i = 0; i < 8; i++) mma_bf16(o[i >> 2][i & 3], pa[i >> 2][0], pa[i >> 2][1], pa[i >> 2][2], pa[i >> 2][3], vf[2 * i], vf[2 * i + 1]);
          if (h == 0) PUMP1() else mbar_wait(bar_done + 30 * 8, par);
          if (NLAYERS > 1) mbar_wait(bar_phi + 8, 0);
#pragma unroll
          for (int i = 0; i < 4; i++) {
            const int hh = i >> 1, dp = i & 1;
            stsm_x4(ta[i],
                    PBIT0(pack_bf16(o[hh][dp * 2][0], o[hh][dp * 2][1])), PBIT0(pack_bf16(o[hh][dp * 2][2], o[hh][dp * 2][3])),
                    PBIT1(pack_bf16(o[hh][dp * 2 + 1][0], o[hh][dp * 2 + 1][1])), PBIT1(pack_bf16(o[hh][dp * 2 + 1][2], o[hh][dp * 2 + 1][3])));
          }
          PUBLISH_O();
          PROF(11 + h * 12);
          if (h) break;
          REST_P1(ASKEW);
          asm volatile("cp.async.bulk.wait_group.read 0;" ::: "memory");
          DRAIN_A(S1, 1, {});
        }
      } else {
        constexpr uint32_t par = 1;
        float st[32];
        const float c0 = rs0 * LOG2E, c1 = rs1 * LOG2E;
        { V_ADDR(pV); STAGE_V(S0 + 64); }
        if (warp < 2) sts128(sbase + OFF_ONES + warp * 512 + lane * 16, 0x3F803F80u, 0x3F803F80u, 0x3F803F80u, 0x3F803F80u);
        scale32(st, S0, c0, c1);
        PIN(st, 32);
#define KV_MMA(vs) { \
          const uint32_t dp = dA0 + 12 * 1024 - wg * 2560, dv = dA0 + (vs) * 1024 + ((OFF_ONES - (vs) * SLOT - 16) << 12) - wg * (512 << 16); \
          STG_WAIT(); \
          wgmma_fence(); \
          _Pragma("unroll") for (int ks = 0; ks < 8; ks++) { \
            const uint64_t a = DESC(dp + ks * 128, 0x40000040), b = DESC(dv + ks * (64 - (64 << 16)), 0x80000020); \
            if (ks == 0) wgmma_n40<0, 1>(kv, a, b); else wgmma_n40<1, 1>(kv, a, b); } \
          wgmma_commit(); }
#define KV_RED(hp) { \
          float* kvg = g_kv[l >> 1] + (jj * 4 + (hp) * 2) * KVH + warp * 768 + lane * 4; \
          _Pragma("unroll") for (int i = 0; i < 5; i++) red_v4(kvg + i * 128, kv[i * 3], kv[i * 3 + 1], kv[i * 3 + 2], 1.f); \
          red_v4(kvg + 640, kv[15], kv[16], kv[18], 1.f); }
#define KV_LOAD(hp) { \
          const uint4* kvg = reinterpret_cast<const uint4*>(g_kv[l >> 1] + (jj * 4 + (hp) * 2) * KVH) + warp * 192 + lane; \
          _Pragma("unroll") for (int i = 0; i < 6; i++) v[i] = ld_b128(kvg + i * 32); }
#define KVV(i) __uint_as_float((i) % 3 == 0 ? v[(i) / 3].x : ((i) % 3 == 1 ? v[(i) / 3].y : v[(i) / 3].z))
#define KV_TILE(hp) { \
          _Pragma("unroll 1") for (int it = 0; it < (1 << 16); it++) { \
            if (__all_sync(0xffffffffu, (v[0].w & v[1].w & v[2].w & v[3].w & v[4].w & v[5].w) == 0x41800000u)) break; \
            RETRY_COUNT(); \
            KV_LOAD(hp); \
          } \
          PROF(25 + (hp)); \
          const uint32_t e = lane & 7, jt = ((lane >> 1) & 4) + (e >> 1); \
          const uint32_t row = ((((warp >> 1) ^ wg) & 1) << 5) + ((jt & 1) << 4) + ((warp & 1) << 3) + (jt & 6) + (e & 1); \
          const uint32_t kd = pV + wg * 8192 + row * 128, ksw = (row & 7) << 4; \
          _Pragma("unroll") for (int i = 0; i < 2; i++) \
            stsm_x4(kd + ((i * 32 + lhi) ^ ksw), pack_bf16(KVV(i * 8), KVV(i * 8 + 1)), pack_bf16(KVV(i * 8 + 2), KVV(i * 8 + 3)), \
                    pack_bf16(KVV(i * 8 + 4), KVV(i * 8 + 5)), pack_bf16(KVV(i * 8 + 6), KVV(i * 8 + 7))); \
          stsm_x4(kd + ((64u + lhi) ^ ksw), pack_bf16(KVV(16), 1.f), pack_bf16(KVV(17), 1.f), 0u, 0u); }
#pragma unroll 1
        for (int h = 0; h < 2; h++) {
          PROF(4 + h * 2);
          SITE(0);
          LANE_CONSTS();
          const uint32_t dsw = (uint32_t)(g ^ (2 * t)) << 4, dst = ((t & 2) ? pK : sbase + 12 * SLOT) + (r0 + g) * 128;
          float e[16], f[16];
          float sa = exps16_<0>(e, st);
          exps16_fix<0>(e, st, sa);
          asm volatile("" : "+f"(sa)); PIN(e, 16); SITE(1);
          if (h) STG_WAIT();
          store16(e, sa, dst, dsw, 4);
          float sb = exps16_<1>(f, st);
          exps16_fix<1>(f, st, sb);
          asm volatile("" : "+f"(sb)); PIN(f, 16); SITE(2);
          store16(f, sb, dst, dsw, 0);
          float sc = exps16_<0>(e, st + 2);
          exps16_fix<0>(e, st + 2, sc);
          asm volatile("" : "+f"(sc)); PIN(e, 16); SITE(3);
          store16(e, sc, dst + 1024, dsw, 4);
          float sd = exps16_<1>(f, st + 2);
          exps16_fix<1>(f, st + 2, sd);
          asm volatile("" : "+f"(sd)); PIN(f, 16); SITE(4);
          store16(f, sd, dst + 1024, dsw, 0);
          PROF(5 + h * 2);
          if (h) break;
          {
            float kv[20];
            ACC_DEF(kv, 20);
            fence_proxy_async_smem();
            STG_ARRIVE();
            KV_MMA(11);
            PUMP0();
            ACC_FENCE(kv, 20);
            KV_RED(0);
            STG_ARRIVE();
          }
          scale32(st, S0 + 32, c0, c1);
          PIN(st, 32);
        }
        bool big;
        uint4 v[6];
        {
          float kv[20];
          if (KT0) { LANE_CONSTS(); KV_LOAD(0); }
          mbar_wait(bar_stat2, par);
          LNSTEP(S1, 1);
          ub = bar_full + 240;
          PUMP1();
          if (wg == 0) bar_sync<BAR_SKEW, 256>();
          QSTEP(S1, RA_CUR, 1, {});
          if (wg == 1) bar_arrive<BAR_SKEW, 256>();
          QREL();
          if (KT0 == 2) { LANE_CONSTS(); KV_TILE(0); }
          LANE_CONSTS();
          V_ADDR(sbase + 3 * SLOT);
          PINU(va_, 2);
          mbar_wait(bar_done + 30 * 8, par);
          wgmma_wait<0>();
          ACC_FENCE(S1, 96);
          if (!(RLATE & 2)) REL(bar_done + 31 * 8);
          PROF(13);
          STAGE_V(S1 + 64);
          fence_proxy_async_smem();
          STG_ARRIVE();
          if (RLATE & 2) REL(bar_done + 31 * 8);
          scale32(st, S1, c0, c1);
          PIN(st, 32);
          PROF(16);
          ACC_DEF(kv, 20);
          KV_MMA(3);
          SCHED_FENCE();
          if (!KT0) KV_LOAD(0);
          big = any_big(st);
          if (EROT > 0) { phiq_a(st, big); PIN(st, 16); }
          SCHED_FENCE();
          wgmma_wait<0>();
          ACC_FENCE(kv, 20);
          KV_RED(1);
          PROF(17);
        }
#pragma unroll 1
        for (int h = 0; h < 2; h++) {
          const uint32_t pO = sbase + (h ? 3 : 8) * SLOT;
          LANE_CONSTS();
          uint32_t fq[32];
          if (EROT < 1) phiq_a(st, big);
          phiq_b(fq, st, big);
          PINU(fq, 16);
          PROF(18 + h * 14);
          SCHED_FENCE();
          if (h) {
            asm volatile("cp.async.bulk.wait_group.read 0;" ::: "memory");
            mbar_wait(bar_lx, par);
          }
          if (h || KT0 < 2) {
            KV_TILE(h);
            fence_proxy_async_smem();
            STG_ARRIVE();
          }
          SCHED_FENCE();
          phiq_a(st + 16, big); PIN(st + 16, 16);
          if (h || KT0 < 2) STG_WAIT();
          wgmma_wait<0>();
          ACC_FENCE(S1, 64);
          PROF(19 + h * 14);
          float o[4][20];
#define O_MMA(hh) { \
            const uint64_t db = make_desc(pV + (hh) * 8192, 16, 1024); \
            ACC_DEF(o[(hh) * 2], 20); ACC_DEF(o[(hh) * 2 + 1], 20); \
            wgmma_fence(); \
            wgmma_n40_rs<0>(o[(hh) * 2], fq + (hh) * 16, db + 256); wgmma_n40_rs<0>(o[(hh) * 2 + 1], fq + (hh) * 16 + 8, db); \
            wgmma_n40_rs<1>(o[(hh) * 2], fq + (hh) * 16 + 4, db + 384); wgmma_n40_rs<1>(o[(hh) * 2 + 1], fq + (hh) * 16 + 12, db + 128); \
            wgmma_commit(); }
          O_MMA(0);
          SCHED_FENCE();
          phiq_b(fq + 16, st + 16, big); PINU(fq + 16, 16);
          SCHED_FENCE();
          PMASKS(true, O_BIT(l));
#pragma unroll
          for (int hh = 0; hh < 2; hh++) {
            if (hh && !OW) O_MMA(1);
            wgmma_wait<0>();
            ACC_FENCE(o[hh * 2], 20); ACC_FENCE(o[hh * 2 + 1], 20);
            if (!hh && OW) { O_MMA(1); SCHED_FENCE(); }
            const float* x = o[hh * 2];
            const float* y = o[hh * 2 + 1];
            const float rx0 = rcp_fast(x[17]), ry0 = rcp_fast(y[17]), rx1 = rcp_fast(x[19]), ry1 = rcp_fast(y[19]);
            const float i0 = rcp_fast(fmaf(x[16], rx0, y[16] * ry0) + 1e-6f), i1 = rcp_fast(fmaf(x[18], rx1, y[18] * ry1) + 1e-6f);
            const float ax0 = rx0 * i0, ay0 = ry0 * i0, ax1 = rx1 * i1, ay1 = ry1 * i1;
#pragma unroll
            for (int dp = 0; dp < 2; dp++)
              stsm_x4(pO + srowoff + ((hh * 64 + dp * 32 + lhi) ^ lsw),
                      PBIT0(pack_bf16(fmaf(x[dp * 8], ax0, y[dp * 8] * ay0), fmaf(x[dp * 8 + 1], ax0, y[dp * 8 + 1] * ay0))),
                      PBIT0(pack_bf16(fmaf(x[dp * 8 + 2], ax1, y[dp * 8 + 2] * ay1), fmaf(x[dp * 8 + 3], ax1, y[dp * 8 + 3] * ay1))),
                      PBIT1(pack_bf16(fmaf(x[dp * 8 + 4], ax0, y[dp * 8 + 4] * ay0), fmaf(x[dp * 8 + 5], ax0, y[dp * 8 + 5] * ay0))),
                      PBIT1(pack_bf16(fmaf(x[dp * 8 + 6], ax1, y[dp * 8 + 6] * ay1), fmaf(x[dp * 8 + 7], ax1, y[dp * 8 + 7] * ay1))));
          }
          PUBLISH_O();
          PROF(20 + h * 14);
          if (h) break;
          if (KVL == 2) { KV_LOAD(1); SCHED_FENCE(); }
          scale32(st, S1 + 32, c0, c1);
          PIN(st, 32);
          LOAD_X();
          bar_wg(wg);
          WSTEP();
          SCHED_FENCE();
          if (KVL == 0) KV_LOAD(1);
          big = any_big(st);
          if (KVL == 1) { SCHED_FENCE(); KV_LOAD(1); }
          if (EROT > 0) { phiq_a(st, big); PIN(st, 16); }
          PROF(31);
        }
      }
      __syncwarp();
      if (elect_one()) mbar_arrive_local(bar_epi);
      bar_wg(wg);
#pragma unroll 1
      while (ub < bar_full + 384) {
        WSTEP();
        if (ub == bar_full + 8 * 41) { asm volatile("cp.async.bulk.wait_group.read 0;" ::: "memory"); PROF(35); }
        if (ub == bar_full + 8 * 42) PROF(36);
      }
      {
        LANE_CONSTS();
        TILE_CONSTS(pK, l < NLAYERS - 1, X_BIT(l));
        wgmma_wait<0>();
        ACC_FENCE(S1, 64);
        if (!RLATE) REL(bar_done + 47 * 8);
        PROF(37);
        X_OUT(0);
        WARP_STORE(l < NLAYERS - 1 ? &tm_os : &tm_xo, pK, jj * 128, mm * 128 + (l < NLAYERS - 1 ? S_LEN : 0));
        if (RLATE) REL(bar_done + 47 * 8);
        if (l == NLAYERS - 1) {
          X_OUT(1);
          WARP_STORE(&tm_xo, pV, jj * 128 + 64, mm * 128);
          if (FINW) asm volatile("cp.async.bulk.wait_group 0;" ::: "memory"); else asm volatile("cp.async.bulk.wait_group.read 0;" ::: "memory");
        }
      }
#pragma unroll
      for (int i = 32; i < 64; i++) { uint32_t c; asm volatile("mov.b32 %0, %1;" : "=r"(c) : "f"(S1[i])); S1[i] = __uint_as_float(c); }
      PROF(38);
    }
    cluster_sync();
  }
}

typedef CUresult (*PFN_encode)(CUtensorMap*, CUtensorMapDataType, cuuint32_t, void*, const cuuint64_t*, const cuuint64_t*,
                               const cuuint32_t*, const cuuint32_t*, CUtensorMapInterleave, CUtensorMapSwizzle,
                               CUtensorMapL2promotion, CUtensorMapFloatOOBfill);

CUtensorMap make_map(PFN_encode enc, const void* ptr, uint64_t inner, uint64_t outer, uint32_t box_inner, uint32_t box_outer,
                     CUtensorMapSwizzle swz = CU_TENSOR_MAP_SWIZZLE_128B) {
  CUtensorMap m;
  cuuint64_t dims[2] = {inner, outer};
  cuuint64_t strides[1] = {inner * 2};
  cuuint32_t box[2] = {box_inner, box_outer};
  cuuint32_t es[2] = {1, 1};
  enc(&m, CU_TENSOR_MAP_DATA_TYPE_BFLOAT16, 2, const_cast<void*>(ptr), dims, strides, box, es, CU_TENSOR_MAP_INTERLEAVE_NONE,
      swz, CU_TENSOR_MAP_L2_PROMOTION_L2_256B, CU_TENSOR_MAP_FLOAT_OOB_FILL_NONE);
  return m;
}

}

extern "C" void kernel_launch(void* const* d_in, const int* in_sizes, int n_in, void* d_out, int out_size) {
  (void)in_sizes; (void)n_in; (void)out_size;
  static PFN_encode enc = nullptr;
  if (!enc) {
    void* fn = nullptr;
    cudaDriverEntryPointQueryResult qr;
    cudaGetDriverEntryPoint("cuTensorMapEncodeTiled", &fn, cudaEnableDefault, &qr);
    enc = (PFN_encode)fn;
    cudaFuncSetAttribute(mega_kernel, cudaFuncAttributeMaxDynamicSharedMemorySize, SMEM_BYTES);
  }
  Params prm;
  prm.x0 = (const __nv_bfloat16*)d_in[0];
  prm.wA_qkv = (const __nv_bfloat16*)d_in[1];
  prm.wA_o = (const __nv_bfloat16*)d_in[2];
  prm.wB_qkv = (const __nv_bfloat16*)d_in[4];
  prm.wB_phi = (const __nv_bfloat16*)d_in[5];
  prm.wB_o = (const __nv_bfloat16*)d_in[6];
  prm.out = (__nv_bfloat16*)d_out;
  void *obuf = nullptr, *wf = nullptr;
  cudaGetSymbolAddress(&obuf, g_obuf);
  cudaGetSymbolAddress(&wf, g_wfold);
  CUtensorMap tm_x0 = make_map(enc, d_in[0], D_MODEL, S_LEN, 64, 128);
  CUtensorMap tm_xo = make_map(enc, d_out, D_MODEL, S_LEN, 64, 16);
  CUtensorMap tm_os = make_map(enc, obuf, D_MODEL, 2 * S_LEN, 64, 16);
  CUtensorMap tm_o = make_map(enc, obuf, D_MODEL, 2 * S_LEN, 64, 128);
  CUtensorMap tm_wf = make_map(enc, wf, 2048, D_MODEL, 64, 32);
  CUtensorMap tm_wqA = make_map(enc, d_in[1], 3 * D_MODEL, D_MODEL, 64, 32);
  CUtensorMap tm_wqB = make_map(enc, prm.wB_qkv, 3 * D_MODEL, D_MODEL, 64, 32);
  CUtensorMap tm_woA = make_map(enc, prm.wA_o, D_MODEL, D_MODEL, 64, 64);
  CUtensorMap tm_woB = make_map(enc, prm.wB_o, D_MODEL, D_MODEL, 64, 64);
  CUtensorMap tm_phi = make_map(enc, prm.wB_phi, 32, 1024, 32, 128, CU_TENSOR_MAP_SWIZZLE_64B);
  mega_kernel<<<NMAIN + NAUX, 384, SMEM_BYTES>>>(tm_x0, tm_xo, tm_os, tm_o, tm_wf, tm_wqA, tm_wqB, tm_woA, tm_woB, tm_phi, prm);
}
```

```cpp
#include <cuda_runtime.h>
#include <cuda.h>
#include <cuda_bf16.h>
#include <stdint.h>

#define NLAYERS 4

#define STAG1 0
#define HPUMP1 2
#define HPUMP2 1
#define ASKEW 2
#define FPUMP 3
#define PFGAP 100
#define POLLGAP 120
#define OW 1
#define AW0 1
#define RLATE 3
#define FSTART 0
#define MAPV 1
#define HW1 29
#define XPACE 0x06050401000000ull
#define XP0 4
#define HW0 18
#define XD 4
#define WFGAP 50
#define KT0 2
#define W23 0
#define AX 0
#define PF0 1
#define EARLY 2
#define BIGLIM 3600.f
#define SUMLO 0x1p-100f
#define SUMHI 0x1p100f
#define EROT 1
#define FINW 0
#define AHOIST 1
#define EMRG 1
#define KVL 0
#define BMASK 0x1F
#define ASITE 1
namespace {

constexpr int S_LEN = 2048, D_MODEL = 1024;
constexpr int NAUX = 4, NMAIN = 128;
constexpr int SLOT = 16384;
constexpr int QST = 24576;
constexpr int OFF_RA = 6 * SLOT, OFF_S = 10 * SLOT;
constexpr int OFF_HALO = 13 * SLOT, OFF_LNB = OFF_HALO  , OFF_ONES = OFF_HALO + 3072;
constexpr int OFF_ST = OFF_HALO + 7168  , OFF_PHI = OFF_HALO + 8192;
constexpr int OFF_BAR = 14 * SLOT;
constexpr int OFF_LNA = OFF_BAR + 1024;
constexpr int SMEM_BYTES = OFF_LNA + 2048;
#define WO_ASLOT(par) ((par) ? 0x9876CAB39876CA98ull : 0x98C76BA398C7698Cull)
constexpr unsigned long long WO_BSLOT = 0x5432105421054210ull;
__device__ __forceinline__ int srcb(int j, int i) { return (i + (i >= j)) & 7; }
__device__ __forceinline__ int kslice(int j, int i) { return i < 2 ? 2 * j + i : (i < 9 ? 2 * srcb(j, i - 2) : 2 * srcb(j, i - 9) + 1); }
__device__ __forceinline__ int wslice(int j, int s) { return 2 * ((s & 7) ? srcb(j, (s & 7) - 1) : j) + (s >> 3); }
constexpr int KVH = 6 * 128 * 4;

struct __align__(128) Flag { unsigned v; unsigned pad[31]; };
struct Flags {
  Flag xready[4][16];
  Flag wfready[8];
  Flag done;
  Flag epoch;
};

__device__ Flags g_flags;
__device__ __nv_bfloat16 g_obuf[2 * S_LEN * D_MODEL];
#define O_BIT(l) ((epoch * NLAYERS + (l) + 1) & 1u)
#define X_BIT(l) ((epoch * (NLAYERS - 1) + (l) + 1) & 1u)
__device__ __nv_bfloat16 g_wfold[D_MODEL * 2048];
__device__ uint4 g_halo[16 * 8 * 512];
__device__ __align__(128) float g_kv[2][32 * KVH];
__device__ __align__(128) uint2 g_colsum[2][1536][2];
__device__ __align__(128) uint2 g_stats[S_LEN * 8];
#define H_BIT(l) (NLAYERS > 2 ? (uint32_t)((l) == 0) : (ep1 & 1))
#define STAT_TAG(l) ((ep1 * NLAYERS + (l) + 1) & 3u)

#define RETRY_COUNT()
#define PRL 0
#define PRU 0
#define PROFL 1
#define PROFW 0
#define PROFT(i) do {} while (0)
#define PROF(i) do {} while (0)

__device__ __forceinline__ uint32_t smem_u32(const void* p) { return (uint32_t)__cvta_generic_to_shared(p); }
__device__ __forceinline__ bool elect_one() {
  uint32_t p;
  asm volatile("{\n.reg .pred p;\nelect.sync _|p, 0xffffffff;\nselp.u32 %0, 1, 0, p;\n}\n" : "=r"(p));
  return p != 0;
}
__device__ __forceinline__ void mbar_init(uint32_t bar, uint32_t cnt) {
  asm volatile("mbarrier.init.shared::cta.b64 [%0], %1;" :: "r"(bar), "r"(cnt));
}
__device__ __forceinline__ void mbar_expect_tx(uint32_t bar, uint32_t bytes) {
  asm volatile("mbarrier.arrive.expect_tx.shared::cta.b64 _, [%0], %1;" :: "r"(bar), "r"(bytes) : "memory");
}
#define mbar_wait(bar, parity) \
  asm volatile("{\n.reg .pred p, q;\nW_%=:\nmbarrier.try_wait.parity.shared::cta.b64 p, [%1], %2;\nadd.s32 %0, %0, -1;\n" \
               "setp.gt.and.s32 q, %0, 0, !p;\n@q bra.uni W_%=;\n}\n" : "+r"(budget) : "r"((uint32_t)(bar)), "r"((uint32_t)(parity)) : "memory")
#define mbar_wait_sl(bar, parity) \
  asm volatile("{\n.reg .pred p, q;\nW_%=:\nmbarrier.try_wait.parity.shared::cta.b64 p, [%1], %2, 20000;\nadd.s32 %0, %0, -64;\n" \
               "setp.gt.and.s32 q, %0, 0, !p;\n@q bra.uni W_%=;\n}\n" : "+r"(budget) : "r"((uint32_t)(bar)), "r"((uint32_t)(parity)) : "memory")
__device__ __forceinline__ void mbar_arrive_local(uint32_t bar) {
  asm volatile("mbarrier.arrive.shared::cta.b64 _, [%0];" :: "r"(bar) : "memory");
}
__device__ __forceinline__ void tma_load_2d(uint32_t dst, const CUtensorMap* tm, uint32_t bar, int c0, int c1) {
  asm volatile("cp.async.bulk.tensor.2d.shared::cluster.global.mbarrier::complete_tx::bytes [%0], [%1, {%3, %4}], [%2];"
               :: "r"(dst), "l"(tm), "r"(bar), "r"(c0), "r"(c1) : "memory");
}
__device__ __forceinline__ void tma_load_2d_mc(uint32_t dst, const CUtensorMap* tm, uint32_t bar, int c0, int c1) {
  asm volatile("cp.async.bulk.tensor.2d.shared::cluster.global.mbarrier::complete_tx::bytes.multicast::cluster [%0], [%1, {%3, %4}], [%2], %5;"
               :: "r"(dst), "l"(tm), "r"(bar), "r"(c0), "r"(c1), "h"((uint16_t)3) : "memory");
}
__device__ __forceinline__ void tma_store_2d(const CUtensorMap* tm, uint32_t src, int c0, int c1) {
  asm volatile("cp.async.bulk.tensor.2d.global.shared::cta.bulk_group [%0, {%2, %3}], [%1];"
               :: "l"(tm), "r"(src), "r"(c0), "r"(c1) : "memory");
}
__device__ __forceinline__ void bulk_commit_wait() {
  asm volatile("cp.async.bulk.commit_group;\ncp.async.bulk.wait_group 0;" ::: "memory");
}
__device__ __forceinline__ void prefetch_tmap(const CUtensorMap* tm) {
  asm volatile("prefetch.tensormap [%0];" :: "l"(tm) : "memory");
}
__device__ __forceinline__ void fence_proxy_async_global() { asm volatile("fence.proxy.async.global;" ::: "memory"); }
__device__ __forceinline__ void fence_proxy_async_smem() { asm volatile("fence.proxy.async.shared::cta;" ::: "memory"); }
__device__ __forceinline__ unsigned ld_relaxed(const unsigned* p) {
  unsigned v;
  asm volatile("ld.relaxed.gpu.global.u32 %0, [%1];" : "=r"(v) : "l"(p) : "memory");
  return v;
}
__device__ __forceinline__ void fence_acquire() { asm volatile("fence.acquire.gpu;" ::: "memory"); }
__device__ __forceinline__ void wait_flag(const unsigned* p, unsigned target) {
  int it = 0;
  while ((int)(ld_relaxed(p) - target) < 0 && ++it < (1 << 20)) {}
  fence_acquire();
}
__device__ __forceinline__ void signal_release(unsigned* p) {
  asm volatile("red.release.gpu.global.add.u32 [%0], 1;" :: "l"(p) : "memory");
}
template <int ID, int N> __device__ __forceinline__ void bar_arrive() { asm volatile("bar.arrive %0, %1;" :: "n"(ID), "n"(N) : "memory"); }
template <int ID, int N> __device__ __forceinline__ void bar_sync() { asm volatile("bar.sync %0, %1;" :: "n"(ID), "n"(N) : "memory"); }
__device__ __forceinline__ void bar_wg(int wg) { asm volatile("bar.sync %0, 128;" :: "r"(2 + wg) : "memory"); }
__device__ __forceinline__ void cluster_sync() {
  asm volatile("barrier.cluster.arrive.relaxed.aligned;\nbarrier.cluster.wait.aligned;" ::: "memory");
}
__device__ __forceinline__ void cluster_wait() { asm volatile("barrier.cluster.wait.acquire.aligned;" ::: "memory"); }
enum { BAR_X1 = 7, BAR_WF = 8  , BAR_SKEW = 10 };

__device__ __forceinline__ void wgmma_fence() { asm volatile("wgmma.fence.sync.aligned;" ::: "memory"); }
__device__ __forceinline__ void wgmma_commit() { asm volatile("wgmma.commit_group.sync.aligned;" ::: "memory"); }
template <int N> __device__ __forceinline__ void wgmma_wait() { asm volatile("wgmma.wait_group.sync.aligned %0;" :: "n"(N) : "memory"); }

template <int scale_d, int tnsp_b = 1> __device__ __forceinline__ void wgmma_n192(float* d, uint64_t descA, uint64_t descB) {
  asm volatile("{\n.reg .pred p;\nsetp.ne.b32 p, %98, 0;\n"
               "wgmma.mma_async.sync.aligned.m64n192k16.f32.bf16.bf16 {%0,%1,%2,%3,%4,%5,%6,%7,%8,%9,%10,%11,%12,%13,%14,%15,%16,%17,%18,%19,%20,%21,%22,%23,%24,%25,%26,%27,%28,%29,%30,%31,%32,%33,%34,%35,%36,%37,%38,%39,%40,%41,%42,%43,%44,%45,%46,%47,%48,%49,%50,%51,%52,%53,%54,%55,%56,%57,%58,%59,%60,%61,%62,%63,%64,%65,%66,%67,%68,%69,%70,%71,%72,%73,%74,%75,%76,%77,%78,%79,%80,%81,%82,%83,%84,%85,%86,%87,%88,%89,%90,%91,%92,%93,%94,%95}, %96, %97, p, 1, 1, 0, %99;\n}\n"
               : "+f"(d[0]), "+f"(d[1]), "+f"(d[2]), "+f"(d[3]), "+f"(d[4]), "+f"(d[5]), "+f"(d[6]), "+f"(d[7]), "+f"(d[8]), "+f"(d[9]), "+f"(d[10]), "+f"(d[11]), "+f"(d[12]), "+f"(d[13]), "+f"(d[14]), "+f"(d[15]), "+f"(d[16]), "+f"(d[17]), "+f"(d[18]), "+f"(d[19]), "+f"(d[20]), "+f"(d[21]), "+f"(d[22]), "+f"(d[23]), "+f"(d[24]), "+f"(d[25]), "+f"(d[26]), "+f"(d[27]), "+f"(d[28]), "+f"(d[29]), "+f"(d[30]), "+f"(d[31]), "+f"(d[32]), "+f"(d[33]), "+f"(d[34]), "+f"(d[35]), "+f"(d[36]), "+f"(d[37]), "+f"(d[38]), "+f"(d[39]), "+f"(d[40]), "+f"(d[41]), "+f"(d[42]), "+f"(d[43]), "+f"(d[44]), "+f"(d[45]), "+f"(d[46]), "+f"(d[47]), "+f"(d[48]), "+f"(d[49]), "+f"(d[50]), "+f"(d[51]), "+f"(d[52]), "+f"(d[53]), "+f"(d[54]), "+f"(d[55]), "+f"(d[56]), "+f"(d[57]), "+f"(d[58]), "+f"(d[59]), "+f"(d[60]), "+f"(d[61]), "+f"(d[62]), "+f"(d[63]), "+f"(d[64]), "+f"(d[65]), "+f"(d[66]), "+f"(d[67]), "+f"(d[68]), "+f"(d[69]), "+f"(d[70]), "+f"(d[71]), "+f"(d[72]), "+f"(d[73]), "+f"(d[74]), "+f"(d[75]), "+f"(d[76]), "+f"(d[77]), "+f"(d[78]), "+f"(d[79]), "+f"(d[80]), "+f"(d[81]), "+f"(d[82]), "+f"(d[83]), "+f"(d[84]), "+f"(d[85]), "+f"(d[86]), "+f"(d[87]), "+f"(d[88]), "+f"(d[89]), "+f"(d[90]), "+f"(d[91]), "+f"(d[92]), "+f"(d[93]), "+f"(d[94]), "+f"(d[95])
               : "l"(descA), "l"(descB), "n"(scale_d), "n"(tnsp_b));
}
template <int scale_d> __device__ __forceinline__ void wgmma4_n192(float* d, uint32_t da, uint32_t db) {
#define R_ "{%0,%1,%2,%3,%4,%5,%6,%7,%8,%9,%10,%11,%12,%13,%14,%15,%16,%17,%18,%19,%20,%21,%22,%23,%24,%25,%26,%27,%28,%29,%30,%31,%32,%33,%34,%35,%36,%37,%38,%39,%40,%41,%42,%43,%44,%45,%46,%47,%48,%49,%50,%51,%52,%53,%54,%55,%56,%57,%58,%59,%60,%61,%62,%63,%64,%65,%66,%67,%68,%69,%70,%71,%72,%73,%74,%75,%76,%77,%78,%79,%80,%81,%82,%83,%84,%85,%86,%87,%88,%89,%90,%91,%92,%93,%94,%95}"
  asm volatile("{\n.reg .pred p, q;\n.reg .b64 a, b;\nsetp.ne.b32 p, %98, 0;\nsetp.eq.b32 q, 0, 0;\nmov.b64 a, {%96, 0x40000040};\nmov.b64 b, {%97, 0x40000040};\n"
               "wgmma.mma_async.sync.aligned.m64n192k16.f32.bf16.bf16 " R_ ", a, b, p, 1, 1, 0, 1;\nadd.s64 a, a, 2;\nadd.s64 b, b, 128;\n"
               "wgmma.mma_async.sync.aligned.m64n192k16.f32.bf16.bf16 " R_ ", a, b, q, 1, 1, 0, 1;\nadd.s64 a, a, 2;\nadd.s64 b, b, 128;\n"
               "wgmma.mma_async.sync.aligned.m64n192k16.f32.bf16.bf16 " R_ ", a, b, q, 1, 1, 0, 1;\nadd.s64 a, a, 2;\nadd.s64 b, b, 128;\n"
               "wgmma.mma_async.sync.aligned.m64n192k16.f32.bf16.bf16 " R_ ", a, b, q, 1, 1, 0, 1;\n}\n"
               : "+f"(d[0]), "+f"(d[1]), "+f"(d[2]), "+f"(d[3]), "+f"(d[4]), "+f"(d[5]), "+f"(d[6]), "+f"(d[7]), "+f"(d[8]), "+f"(d[9]), "+f"(d[10]), "+f"(d[11]), "+f"(d[12]), "+f"(d[13]), "+f"(d[14]), "+f"(d[15]), "+f"(d[16]), "+f"(d[17]), "+f"(d[18]), "+f"(d[19]), "+f"(d[20]), "+f"(d[21]), "+f"(d[22]), "+f"(d[23]), "+f"(d[24]), "+f"(d[25]), "+f"(d[26]), "+f"(d[27]), "+f"(d[28]), "+f"(d[29]), "+f"(d[30]), "+f"(d[31]), "+f"(d[32]), "+f"(d[33]), "+f"(d[34]), "+f"(d[35]), "+f"(d[36]), "+f"(d[37]), "+f"(d[38]), "+f"(d[39]), "+f"(d[40]), "+f"(d[41]), "+f"(d[42]), "+f"(d[43]), "+f"(d[44]), "+f"(d[45]), "+f"(d[46]), "+f"(d[47]), "+f"(d[48]), "+f"(d[49]), "+f"(d[50]), "+f"(d[51]), "+f"(d[52]), "+f"(d[53]), "+f"(d[54]), "+f"(d[55]), "+f"(d[56]), "+f"(d[57]), "+f"(d[58]), "+f"(d[59]), "+f"(d[60]), "+f"(d[61]), "+f"(d[62]), "+f"(d[63]), "+f"(d[64]), "+f"(d[65]), "+f"(d[66]), "+f"(d[67]), "+f"(d[68]), "+f"(d[69]), "+f"(d[70]), "+f"(d[71]), "+f"(d[72]), "+f"(d[73]), "+f"(d[74]), "+f"(d[75]), "+f"(d[76]), "+f"(d[77]), "+f"(d[78]), "+f"(d[79]), "+f"(d[80]), "+f"(d[81]), "+f"(d[82]), "+f"(d[83]), "+f"(d[84]), "+f"(d[85]), "+f"(d[86]), "+f"(d[87]), "+f"(d[88]), "+f"(d[89]), "+f"(d[90]), "+f"(d[91]), "+f"(d[92]), "+f"(d[93]), "+f"(d[94]), "+f"(d[95])
               : "r"(da), "r"(db), "n"(scale_d));
#undef R_
}
template <int scale_d> __device__ __forceinline__ void wgmma4_n128(float* d, uint32_t da, uint32_t db) {
#define R_ "{%0,%1,%2,%3,%4,%5,%6,%7,%8,%9,%10,%11,%12,%13,%14,%15,%16,%17,%18,%19,%20,%21,%22,%23,%24,%25,%26,%27,%28,%29,%30,%31,%32,%33,%34,%35,%36,%37,%38,%39,%40,%41,%42,%43,%44,%45,%46,%47,%48,%49,%50,%51,%52,%53,%54,%55,%56,%57,%58,%59,%60,%61,%62,%63}"
  asm volatile("{\n.reg .pred p, q;\n.reg .b64 a, b;\nsetp.ne.b32 p, %66, 0;\nsetp.eq.b32 q, 0, 0;\nmov.b64 a, {%64, 0x40000040};\nmov.b64 b, {%65, 0x40000040};\n"
               "wgmma.mma_async.sync.aligned.m64n128k16.f32.bf16.bf16 " R_ ", a, b, p, 1, 1, 0, 1;\nadd.s64 a, a, 2;\nadd.s64 b, b, 128;\n"
               "wgmma.mma_async.sync.aligned.m64n128k16.f32.bf16.bf16 " R_ ", a, b, q, 1, 1, 0, 1;\nadd.s64 a, a, 2;\nadd.s64 b, b, 128;\n"
               "wgmma.mma_async.sync.aligned.m64n128k16.f32.bf16.bf16 " R_ ", a, b, q, 1, 1, 0, 1;\nadd.s64 a, a, 2;\nadd.s64 b, b, 128;\n"
               "wgmma.mma_async.sync.aligned.m64n128k16.f32.bf16.bf16 " R_ ", a, b, q, 1, 1, 0, 1;\n}\n"
               : "+f"(d[0]), "+f"(d[1]), "+f"(d[2]), "+f"(d[3]), "+f"(d[4]), "+f"(d[5]), "+f"(d[6]), "+f"(d[7]), "+f"(d[8]), "+f"(d[9]), "+f"(d[10]), "+f"(d[11]), "+f"(d[12]), "+f"(d[13]), "+f"(d[14]), "+f"(d[15]), "+f"(d[16]), "+f"(d[17]), "+f"(d[18]), "+f"(d[19]), "+f"(d[20]), "+f"(d[21]), "+f"(d[22]), "+f"(d[23]), "+f"(d[24]), "+f"(d[25]), "+f"(d[26]), "+f"(d[27]), "+f"(d[28]), "+f"(d[29]), "+f"(d[30]), "+f"(d[31]), "+f"(d[32]), "+f"(d[33]), "+f"(d[34]), "+f"(d[35]), "+f"(d[36]), "+f"(d[37]), "+f"(d[38]), "+f"(d[39]), "+f"(d[40]), "+f"(d[41]), "+f"(d[42]), "+f"(d[43]), "+f"(d[44]), "+f"(d[45]), "+f"(d[46]), "+f"(d[47]), "+f"(d[48]), "+f"(d[49]), "+f"(d[50]), "+f"(d[51]), "+f"(d[52]), "+f"(d[53]), "+f"(d[54]), "+f"(d[55]), "+f"(d[56]), "+f"(d[57]), "+f"(d[58]), "+f"(d[59]), "+f"(d[60]), "+f"(d[61]), "+f"(d[62]), "+f"(d[63])
               : "r"(da), "r"(db), "n"(scale_d));
#undef R_
}
template <int scale_d> __device__ __forceinline__ void wgmma_n32(float* d, uint64_t descA, uint64_t descB) {
  asm volatile("{\n.reg .pred p;\nsetp.ne.b32 p, %18, 0;\n"
               "wgmma.mma_async.sync.aligned.m64n32k16.f32.bf16.bf16 {%0,%1,%2,%3,%4,%5,%6,%7,%8,%9,%10,%11,%12,%13,%14,%15}, %16, %17, p, 1, 1, 0, 1;\n}\n"
               : "+f"(d[0]), "+f"(d[1]), "+f"(d[2]), "+f"(d[3]), "+f"(d[4]), "+f"(d[5]), "+f"(d[6]), "+f"(d[7]), "+f"(d[8]), "+f"(d[9]), "+f"(d[10]), "+f"(d[11]), "+f"(d[12]), "+f"(d[13]), "+f"(d[14]), "+f"(d[15])
               : "l"(descA), "l"(descB), "n"(scale_d));
}
template <int scale_d, int tnsp_a> __device__ __forceinline__ void wgmma_n40(float* d, uint64_t descA, uint64_t descB) {
  asm volatile("{\n.reg .pred p;\nsetp.ne.b32 p, %22, 0;\n"
               "wgmma.mma_async.sync.aligned.m64n40k16.f32.bf16.bf16 {%0,%1,%2,%3,%4,%5,%6,%7,%8,%9,%10,%11,%12,%13,%14,%15,%16,%17,%18,%19}, %20, %21, p, 1, 1, %23, 1;\n}\n"
               : "+f"(d[0]), "+f"(d[1]), "+f"(d[2]), "+f"(d[3]), "+f"(d[4]), "+f"(d[5]), "+f"(d[6]), "+f"(d[7]), "+f"(d[8]), "+f"(d[9]), "+f"(d[10]), "+f"(d[11]), "+f"(d[12]), "+f"(d[13]), "+f"(d[14]), "+f"(d[15]), "+f"(d[16]), "+f"(d[17]), "+f"(d[18]), "+f"(d[19])
               : "l"(descA), "l"(descB), "n"(scale_d), "n"(tnsp_a));
}
template <int scale_d> __device__ __forceinline__ void wgmma_n40_rs(float* d, const uint32_t* a, uint64_t descB) {
  asm volatile("{\n.reg .pred p;\nsetp.ne.b32 p, %25, 0;\n"
               "wgmma.mma_async.sync.aligned.m64n40k16.f32.bf16.bf16 {%0,%1,%2,%3,%4,%5,%6,%7,%8,%9,%10,%11,%12,%13,%14,%15,%16,%17,%18,%19}, {%20,%21,%22,%23}, %24, p, 1, 1, 1;\n}\n"
               : "+f"(d[0]), "+f"(d[1]), "+f"(d[2]), "+f"(d[3]), "+f"(d[4]), "+f"(d[5]), "+f"(d[6]), "+f"(d[7]), "+f"(d[8]), "+f"(d[9]), "+f"(d[10]), "+f"(d[11]), "+f"(d[12]), "+f"(d[13]), "+f"(d[14]), "+f"(d[15]), "+f"(d[16]), "+f"(d[17]), "+f"(d[18]), "+f"(d[19])
               : "r"(a[0]), "r"(a[1]), "r"(a[2]), "r"(a[3]), "l"(descB), "n"(scale_d));
}
__device__ __forceinline__ uint64_t make_desc(uint32_t addr, uint32_t lbo_bytes, uint32_t sbo_bytes) {
  return (uint64_t)((addr & 0x3FFFF) >> 4) | ((uint64_t)(lbo_bytes >> 4) << 16) | ((uint64_t)(sbo_bytes >> 4) << 32) | (1ull << 62);
}

__device__ __forceinline__ void ldsm_x4(uint32_t addr, uint32_t& r0, uint32_t& r1, uint32_t& r2, uint32_t& r3) {
  asm volatile("ldmatrix.sync.aligned.m8n8.x4.shared.b16 {%0,%1,%2,%3}, [%4];" : "=r"(r0), "=r"(r1), "=r"(r2), "=r"(r3) : "r"(addr) : "memory");
}
__device__ __forceinline__ void ldsm_x4_t(uint32_t addr, uint32_t& r0, uint32_t& r1, uint32_t& r2, uint32_t& r3) {
  asm volatile("ldmatrix.sync.aligned.m8n8.x4.trans.shared.b16 {%0,%1,%2,%3}, [%4];" : "=r"(r0), "=r"(r1), "=r"(r2), "=r"(r3) : "r"(addr) : "memory");
}
__device__ __forceinline__ void stsm_x4(uint32_t addr, uint32_t r0, uint32_t r1, uint32_t r2, uint32_t r3) {
  asm volatile("stmatrix.sync.aligned.m8n8.x4.shared.b16 [%0], {%1,%2,%3,%4};" :: "r"(addr), "r"(r0), "r"(r1), "r"(r2), "r"(r3) : "memory");
}
__device__ __forceinline__ void sts128(uint32_t addr, uint32_t a, uint32_t b, uint32_t c, uint32_t d) {
  asm volatile("st.shared.v4.u32 [%0], {%1,%2,%3,%4};" :: "r"(addr), "r"(a), "r"(b), "r"(c), "r"(d) : "memory");
}
__device__ __forceinline__ float lds32f(uint32_t addr) {
  float v;
  asm volatile("ld.shared.f32 %0, [%1];" : "=f"(v) : "r"(addr) : "memory");
  return v;
}
__device__ __forceinline__ void sts32f(uint32_t addr, float a) {
  asm volatile("st.shared.f32 [%0], %1;" :: "r"(addr), "f"(a) : "memory");
}
__device__ __forceinline__ void mma_bf16(float (&c)[4], uint32_t a0, uint32_t a1, uint32_t a2, uint32_t a3, uint32_t b0, uint32_t b1) {
  asm volatile("mma.sync.aligned.m16n8k16.row.col.f32.bf16.bf16.f32 {%0,%1,%2,%3}, {%4,%5,%6,%7}, {%8,%9}, {%0,%1,%2,%3};"
               : "+f"(c[0]), "+f"(c[1]), "+f"(c[2]), "+f"(c[3]) : "r"(a0), "r"(a1), "r"(a2), "r"(a3), "r"(b0), "r"(b1));
}
__device__ __forceinline__ void mma_bf16_z(float (&c)[4], uint32_t a0, uint32_t a1, uint32_t a2, uint32_t a3, uint32_t b0, uint32_t b1) {
  asm volatile("mma.sync.aligned.m16n8k16.row.col.f32.bf16.bf16.f32 {%0,%1,%2,%3}, {%4,%5,%6,%7}, {%8,%9}, {%10,%10,%10,%10};"
               : "=f"(c[0]), "=f"(c[1]), "=f"(c[2]), "=f"(c[3]) : "r"(a0), "r"(a1), "r"(a2), "r"(a3), "r"(b0), "r"(b1), "f"(0.f));
}
__device__ __forceinline__ uint32_t movm_t(uint32_t v) {
  uint32_t r;
  asm volatile("movmatrix.sync.aligned.m8n8.trans.b16 %0, %1;" : "=r"(r) : "r"(v));
  return r;
}
__device__ __forceinline__ uint32_t pack_bf16(float lo, float hi) {
  uint32_t r;
  asm("cvt.rn.bf16x2.f32 %0, %1, %2;" : "=r"(r) : "f"(hi), "f"(lo));
  return r;
}
__device__ __forceinline__ float bf_lo(uint32_t v) { return __uint_as_float(v << 16); }
__device__ __forceinline__ float bf_hi(uint32_t v) { return __uint_as_float(v & 0xFFFF0000u); }
__device__ __forceinline__ void split3(float x, uint32_t& h, uint32_t& m, uint32_t& l) {
  h = pack_bf16(x, 0.f); x -= bf_lo(h);
  m = pack_bf16(x, 0.f); x -= bf_lo(m);
  l = pack_bf16(x, 0.f);
}
__device__ __forceinline__ float ex2(float x) { float r; asm("ex2.approx.ftz.f32 %0, %1;" : "=f"(r) : "f"(x)); return r; }
__device__ __forceinline__ float rcp_fast(float x) { float r; asm("rcp.approx.ftz.f32 %0, %1;" : "=f"(r) : "f"(x)); return r; }
__device__ __forceinline__ void red_v4(float* p, float a, float b, float c, float d) {
  asm volatile("red.global.add.v4.f32 [%0], {%1, %2, %3, %4};" :: "l"(p), "f"(a), "f"(b), "f"(c), "f"(d) : "memory");
}
__device__ __forceinline__ uint4 ld_ll(const uint4* p) {
  uint4 v;
  asm volatile("{\n.reg .b64 a, b;\nld.relaxed.gpu.global.v2.b64 {a, b}, [%4];\nmov.b64 {%0, %1}, a;\nmov.b64 {%2, %3}, b;\n}\n"
               : "=r"(v.x), "=r"(v.y), "=r"(v.z), "=r"(v.w) : "l"(p) : "memory");
  return v;
}
__device__ __forceinline__ void st_b64(uint2* p, uint32_t a, uint32_t b) {
  asm volatile("{\n.reg .b64 v;\nmov.b64 v, {%1, %2};\nst.relaxed.gpu.global.b64 [%0], v;\n}\n" :: "l"(p), "r"(a), "r"(b) : "memory");
}
__device__ __forceinline__ void st_b128(uint4* p, uint32_t a, uint32_t b, uint32_t c, uint32_t d) {
  asm volatile("{\n.reg .b128 v;\nmov.b128 v, {%1, %2, %3, %4};\nst.relaxed.gpu.global.b128 [%0], v;\n}\n" :: "l"(p), "r"(a), "r"(b), "r"(c), "r"(d) : "memory");
}
__device__ __forceinline__ uint4 ld_b128(const uint4* p) {
  uint4 v;
  asm volatile("{\n.reg .b128 v;\nld.relaxed.gpu.global.b128 v, [%4];\nmov.b128 {%0, %1, %2, %3}, v;\n}\n" : "=r"(v.x), "=r"(v.y), "=r"(v.z), "=r"(v.w) : "l"(p) : "memory");
  return v;
}

constexpr float LOG2E = 1.4426950408889634f;

struct Params {
  const __nv_bfloat16* x0;
  const __nv_bfloat16* wA_qkv;
  const __nv_bfloat16* wA_o;
  const __nv_bfloat16* wB_qkv;
  const __nv_bfloat16* wB_phi;
  const __nv_bfloat16* wB_o;
  __nv_bfloat16* out;
};

#define ACC_DEF(d, n) _Pragma("unroll") for (int i_ = 0; i_ < (n); i_++) asm volatile("" : "=f"(d[i_]))
#define ACC_FENCE(d, n) _Pragma("unroll") for (int i_ = 0; i_ < (n); i_++) asm volatile("" : "+f"(d[i_]) :: "memory")
#define PIN(a, n) _Pragma("unroll") for (int i_ = 0; i_ < (n); i_++) asm volatile("" : "+f"((a)[i_]))
#define PINU(a, n) _Pragma("unroll") for (int i_ = 0; i_ < (n); i_++) asm volatile("" : "+r"((a)[i_]))

#define V_ADDR(p0) uint32_t va_[2] = {(p0) + (srowoff >> 1) + (lhi ^ lsw2), (p0) + (srowoff >> 1) + ((32 + lhi) ^ lsw2)}
#define STAGE_V(acc) { \
    _Pragma("unroll") for (int j_ = 0; j_ < 4; j_++) { \
      const float* a_ = (acc) + j_ * 8; \
      stsm_x4(va_[j_ & 1] + (j_ >> 1) * 8192, \
              pack_bf16(rs0 * a_[0], rs0 * a_[1]), pack_bf16(rs1 * a_[2], rs1 * a_[3]), pack_bf16(rs0 * a_[4], rs0 * a_[5]), pack_bf16(rs1 * a_[6], rs1 * a_[7])); } }
#define FRAG(dst, acc, TR, grp) { \
    _Pragma("unroll") for (int i_ = 0; i_ < 16; i_++) { \
      const float r_ = (i_ & 1) ? rs1 : rs0; \
      const uint32_t w_ = pack_bf16(r_ * (acc)[2 * i_], r_ * (acc)[2 * i_ + 1]); \
      if (TR) (dst)[i_] = movm_t(w_); else (dst)[(i_ & 12) + (i_ & 1) * 2 + ((i_ >> 1) & 1)] = w_; } \
    if (warp == 7 && mm < 15) { \
      _Pragma("unroll") for (int j_ = 0; j_ < 4; j_++) \
        st_b128(g_halo + (size_t)(mm * 8 + jj) * 512 + ((grp) * 4 + j_) * 32 + lane, ((dst)[j_ * 4] & ~1u) | H_BIT(l), (dst)[j_ * 4 + 1], (dst)[j_ * 4 + 2], (dst)[j_ * 4 + 3]); } \
    PINU(dst, 16); }
#define FRAG_PUT(src, slot) if (warp < 7) { _Pragma("unroll") for (int j_ = 0; j_ < 4; j_++) \
      sts128(sbase + (slot) * SLOT + 2048 + warp * 2048 + j_ * 512 + lane * 16, (src)[j_ * 4], (src)[j_ * 4 + 1], (src)[j_ * 4 + 2], (src)[j_ * 4 + 3]); }
#define FRAG_GET(dst, slot) { _Pragma("unroll") for (int j_ = 0; j_ < 4; j_++) \
      asm volatile("ld.shared.v4.u32 {%0, %1, %2, %3}, [%4];" : "=r"((dst)[j_ * 4]), "=r"((dst)[j_ * 4 + 1]), "=r"((dst)[j_ * 4 + 2]), "=r"((dst)[j_ * 4 + 3]) \
                   : "r"(sbase + (slot) * SLOT + warp * 2048 + j_ * 512 + lane * 16) : "memory"); }
#define RW(j) (((j) >> 1) * 4 + ((j) & 1))
template <int POS> __device__ __forceinline__ float exps16_(float* o, const float* p) {
  float s[4];
#pragma unroll
  for (int j = 0; j < 16; j++) { o[j] = ex2(POS ? p[RW(j)] : -p[RW(j)]); if (j < 4) s[j] = o[j]; else s[j & 3] += o[j]; }
  const float r = (s[0] + s[1]) + (s[2] + s[3]);
  return r + __shfl_xor_sync(0xffffffffu, r, 1);
}
template <int POS> __device__ __forceinline__ void exps16_fix(float* o, const float* p, float& sum) {
  if (__builtin_expect(__any_sync(0xffffffffu, !(sum > SUMLO && sum < SUMHI)), 0)) {
    float m = p[0], q[32];
#pragma unroll
    for (int j = 1; j < 16; j++) m = POS ? fmaxf(m, p[RW(j)]) : fminf(m, p[RW(j)]);
    const float x = __shfl_xor_sync(0xffffffffu, m, 1);
    m = POS ? fmaxf(m, x) : fminf(m, x);
#pragma unroll
    for (int j = 0; j < 16; j++) q[RW(j)] = p[RW(j)] - m;
    sum = exps16_<POS>(o, q);
  }
}
__device__ __forceinline__ void store16(const float* e, float sum, uint32_t dst, uint32_t dsw, int c0) {
  const float inv = rcp_fast(sum);
#pragma unroll
  for (int j = 0; j < 2; j++)
    sts128(dst + (((c0 + j) << 4) ^ dsw), pack_bf16(e[j * 8] * inv, e[j * 8 + 1] * inv), pack_bf16(e[j * 8 + 2] * inv, e[j * 8 + 3] * inv),
           pack_bf16(e[j * 8 + 4] * inv, e[j * 8 + 5] * inv), pack_bf16(e[j * 8 + 6] * inv, e[j * 8 + 7] * inv));
}
template <int POS> __device__ __forceinline__ void expp16(uint32_t* o, float* p) {
  {
#pragma unroll
    for (int r = 0; r < 4; r += 2) {
      float m = p[r];
#pragma unroll
      for (int j = 1; j < 8; j++) m = POS ? fmaxf(m, p[r + RW(j)]) : fminf(m, p[r + RW(j)]);
#pragma unroll
      for (int s = 1; s <= 2; s <<= 1) { const float x = __shfl_xor_sync(0xffffffffu, m, s); m = POS ? fmaxf(m, x) : fminf(m, x); }
#pragma unroll
      for (int j = 0; j < 8; j++) p[r + RW(j)] -= m;
    }
  }
#pragma unroll
  for (int j = 0; j < 8; j++) o[j] = pack_bf16(ex2(POS ? p[2 * j] : -p[2 * j]), ex2(POS ? p[2 * j + 1] : -p[2 * j + 1]));
}
__device__ __forceinline__ void scale32(float* o, const float* p, float c0, float c1) {
#pragma unroll
  for (int i = 0; i < 32; i++) asm volatile("mul.f32 %0, %1, %2;" : "=f"(o[i]) : "f"(p[i]), "f"((i & 2) ? c1 : c0));
}
__device__ __forceinline__ bool any_big(const float* p) {
  float m[4];
#pragma unroll
  for (int i = 0; i < 32; i++) m[i >> 3] = (i & 7) ? fmaf(p[i], p[i], m[i >> 3]) : p[i] * p[i];
  return __any_sync(0xffffffffu, !(fmaxf(fmaxf(m[0], m[1]), fmaxf(m[2], m[3])) < BIGLIM));
}
__device__ __forceinline__ void phiq_a(float* p, bool big) {
  if (__builtin_expect(!big, 1)) {
#pragma unroll
    for (int j = 0; j < 16; j++) p[j] = ex2(p[j]);
  }
}
template <int NEXT> __device__ __forceinline__ void phiq_b(uint32_t* o, float* p, bool big) {
  if (__builtin_expect(big, 0)) {
    expp16<0>(o, p); expp16<1>(o + 8, p);
  } else {
    if (NEXT) phiq_a(p + 16, false);
#pragma unroll
    for (int j = 0; j < 4; j++) {
      const float a = p[4 * j], b = p[4 * j + 1], c = p[4 * j + 2], d = p[4 * j + 3];
      const float ab = a * b, cd = c * d, r = rcp_fast(ab * cd), x = r * cd, y = r * ab;
      o[2 * j] = pack_bf16(x * b, x * a); o[2 * j + 1] = pack_bf16(y * d, y * c);
      o[8 + 2 * j] = pack_bf16(a, b); o[9 + 2 * j] = pack_bf16(c, d);
    }
  }
}
#define SCHED_FENCE() asm volatile("pmevent 0;" ::: "memory")

__global__ void __cluster_dims__(2, 1, 1) __launch_bounds__(384, 1)
mega_kernel(const __grid_constant__ CUtensorMap tm_x0, const __grid_constant__ CUtensorMap tm_xo, const __grid_constant__ CUtensorMap tm_os,
            const __grid_constant__ CUtensorMap tm_o, const __grid_constant__ CUtensorMap tm_wf,
            const __grid_constant__ CUtensorMap tm_wqA, const __grid_constant__ CUtensorMap tm_wqB,
            const __grid_constant__ CUtensorMap tm_woA, const __grid_constant__ CUtensorMap tm_woB,
            const __grid_constant__ CUtensorMap tm_phi, const Params prm) {
  extern __shared__ __align__(1024) uint8_t smem_raw[];
  const uint32_t sbase = smem_u32(smem_raw);
  const uint32_t bar_full = sbase + OFF_BAR;
  const uint32_t bar_done = bar_full + 384;
  const uint32_t bar_stat = bar_full + 768, bar_stat2 = bar_full + 776, bar_epi = bar_full + 784, bar_phi = bar_full + 936  , bar_halo = bar_full + 904  ;
  const uint32_t bar_xr = bar_full + 800, bar_lx = bar_full + 808, bar_stg = bar_full + 832;
  const uint32_t bar_chk = bar_full + 848;

  const int warp = __shfl_sync(0xffffffffu, threadIdx.x >> 5, 0), lane = threadIdx.x & 31;
  uint32_t rank;
  asm volatile("mov.u32 %0, %%cluster_ctarank;" : "=r"(rank));
  const int aux = (int)blockIdx.x - NMAIN, tp = (int)(blockIdx.x >> 1) - 4;
  const int gp = tp < 0 ? 0 : (tp < 32 ? tp & 7 : 1 + (tp - 32) % 7), me = tp < 0 ? tp + 8 : (tp < 32 ? tp >> 3 : 4 + (tp - 32) / 7);
  const int jj = me, cc = gp;
  const int cta = aux >= 0 ? -1 : (cc * 8 + jj) * 2 + (int)rank;
  const int mm = cc * 2 + (int)rank;

#define LOAD_EPOCH() const unsigned epoch = ld_relaxed(&g_flags.epoch.v), ep1 = epoch + 1; (void)epoch
  int budget = 1 << 22;

  if (cta >= 0) {
    if (warp >= 8 && warp < 8 + EARLY && elect_one()) {
      const int u = warp - 8;
      const uint32_t fb = bar_full + u * 8;
      mbar_init(fb, 1);
      asm volatile("fence.mbarrier_init.release.cluster;" ::: "memory");
      fence_proxy_async_smem();
      mbar_expect_tx(fb, u < 2 ? QST + SLOT : QST);
      if (u < 2) tma_load_2d(sbase + OFF_S + u * SLOT, &tm_x0, fb, jj * 128 + u * 64, mm * 128);
#pragma unroll
      for (int i = 0; i < 6; i++) tma_load_2d(sbase + u * QST + i * 4096, &tm_wqA, fb, jj * 128 + (u >> 1) * 64 + (i >> 1) * 1024, jj * 128 + (u & 1) * 64 + (i & 1) * 32);
      if (u == 0) PROFT(472);
    }
    __syncwarp();
    {
      const int tx = threadIdx.x;
      const __nv_bfloat16* pf = (tx < 128) ? prm.x0 + (size_t)(mm * 128 + tx) * D_MODEL + jj * 128
                                           : prm.wA_qkv + (size_t)(jj * 128 + (tx & 63)) * 3072 + ((tx - 128) >> 6) * 1024 + jj * 128 + rank * 64;
      if (tx < 320) { if (PF0) asm volatile("prefetch.global.L2 [%0];" :: "l"(pf)); }
      else if (tx == 320) prefetch_tmap(&tm_x0);
      else if (tx == 352) prefetch_tmap(&tm_wqA);
      else if (tx == 383) asm volatile("prefetch.global.L2 [%0];" :: "l"(&g_flags.epoch.v));
    }
    if (elect_one()) {
#pragma unroll
      for (int i = 0; i < 4; i++) {
        const int u = warp * 4 + i;
        if (u >= EARLY) mbar_init(bar_full + u * 8, ((u >= 4 && u < 11) || (u > 32 && u != 40)) ? 2 : 1); mbar_init(bar_done + u * 8, 16);
      }
      mbar_init(bar_stat + warp * 16, 0x111111181182ull >> (4 * warp) & 15);
      mbar_init(bar_stat + warp * 16 + 8, 0x111111121811ull >> (4 * warp) & 15);
      mbar_init(bar_chk + 112 + (warp & 7) * 8, 1);
      asm volatile("fence.mbarrier_init.release.cluster;" ::: "memory");
    }
    __syncthreads();
    asm volatile("barrier.cluster.arrive.relaxed.aligned;" ::: "memory");
  }

  if (cta < 0) {
    LOAD_EPOCH();
    const uint32_t buf = sbase + warp * SLOT, bar = sbase + OFF_BAR + warp * 16;
    const uint32_t lsw = (lane & 7) << 4, lhi = (lane >> 4) << 4, lrow = (lane & 15) * 128;
    const bool el = elect_one();
    if (el) {
      mbar_init(bar, 1); mbar_init(bar + 8, 1);
      asm volatile("fence.mbarrier_init.release.cluster;" ::: "memory");
    }
#pragma unroll 1
    for (int rd = 0; rd < (NLAYERS > 1 ? 5 : 2); rd++) {
      if (rd >= 2 && warp >= 8) break;
      const int tk = rd < 2 ? aux * 12 + warp : aux * 8 + warp;
      const int half = tk & 1;
      const int blk = rd < 2 ? (tk >> 1) * 2 + rd : (4 - rd) * 16 + (tk >> 1);
      const CUtensorMap* tm = rd < 2 ? &tm_wqA : (rd == 2 ? &tm_wqB : &tm_wf);
      const int j0 = (blk & 15) >> 1;
#define AUX_LOAD(n) { const uint32_t d_ = buf + ((n) & 1) * 8192, b_ = bar + ((n) & 1) * 8; const int r_ = kslice(j0, 2 * (n) + half) * 64; \
        mbar_expect_tx(b_, 8192); tma_load_2d(d_, tm, b_, blk * 64, r_); tma_load_2d(d_ + 4096, tm, b_, blk * 64, r_ + 32); }
      if (el) {
        if (rd == 3) { wait_flag(&g_flags.wfready[j0].v, ep1 * 16); fence_proxy_async_global(); }
        AUX_LOAD(0); AUX_LOAD(1);
      }
      __syncwarp();
      float cs[8][4];
#pragma unroll
      for (int i = 0; i < 8; i++) cs[i][0] = cs[i][1] = cs[i][2] = cs[i][3] = 0.f;
#pragma unroll 1
      for (int n = 0; n < 8; n++) {
        const uint32_t tb = buf + (n & 1) * 8192 + lrow;
        mbar_wait(bar + (n & 1) * 8, (n >> 1) & 1);
#pragma unroll
        for (int i = 0; i < 16; i++) {
          uint32_t b0, b1, b2, b3;
          ldsm_x4_t(tb + (i >> 2) * 2048 + (((i & 3) * 32 + lhi) ^ lsw), b0, b1, b2, b3);
          mma_bf16(cs[2 * (i & 3)], 0x3F803F80u, 0x3F803F80u, 0x3F803F80u, 0x3F803F80u, b0, b1);
          mma_bf16(cs[2 * (i & 3) + 1], 0x3F803F80u, 0x3F803F80u, 0x3F803F80u, 0x3F803F80u, b2, b3);
        }
        __syncwarp();
        if (el && n < 6) AUX_LOAD(n + 2);
        __syncwarp();
      }
      if (lane < 4) {
#pragma unroll
        for (int i = 0; i < 8; i++) st_b64(&g_colsum[rd >= 2][blk * 32 + i * 4 + lane][half], __float_as_uint(cs[i][0]), (__float_as_uint(cs[i][1]) & ~3u) | (ep1 & 3));
      }
      __syncwarp();
    }
  } else if (warp >= 8) {
    asm volatile("setmaxnreg.dec.sync.aligned.u32 40;");
    if (warp == 8) {
      const bool el = elect_one();
      cluster_wait();
      if (el) {
#pragma unroll 1
        for (int l = 0; l < NLAYERS; l++) {
          const uint32_t par = l & 1;
          const CUtensorMap* tqk = par ? &tm_wf : &tm_wqA;
          const CUtensorMap* tv = par ? &tm_wqB : &tm_wqA;
          const CUtensorMap* two = par ? &tm_woB : &tm_woA;
          if (l == 1) { LOAD_EPOCH(); wait_flag(&g_flags.wfready[jj].v, ep1 * 16); fence_proxy_async_global(); }
#pragma unroll 1
          for (int u = l ? 0 : EARLY; u < 32; u++) {
            if (u >= 4) mbar_wait_sl(bar_done + (u - 4) * 8, par);
            else if (l) mbar_wait_sl(bar_done + (43 + u + (u >> 1)) * 8, par ^ 1);
            else if (u == 1) __nanosleep(STAG1);
            else if (u == 2 && !W23) mbar_wait_sl(bar_full, 0);
            const uint32_t fb = bar_full + u * 8;
            const bool res = u < 4 ? (l || u >= 2) : (u < 11 || (u >= 18 && u < 22));
            mbar_expect_tx(fb, res ? QST : QST + SLOT);
            const int row = kslice(jj, u < 4 ? u & 1 : (u < 18 ? u - 2 : (u < 22 ? u - 6 : u - 20))) * 64 + (int)rank * 32;
            const int ps = u < 4 ? u >> 1 : (u >= 18), col = jj * 128 + ps * 64;
            const int c0 = par ? jj * 128 + (ps ? 0 : 1024) : col;
            const uint32_t dst = sbase + (u & 3) * QST + rank * 4096;
            tma_load_2d_mc(dst, tqk, fb, c0, row);
            tma_load_2d_mc(dst + 8192, tqk, fb, c0 + (par ? 64 : 1024), row);
            tma_load_2d_mc(dst + 16384, tv, fb, col + 2048, row);
            if (l == PRL && u >= PRU && u < PRU + 4) PROFT(473 + u - PRU);
          }
#pragma unroll 1
          for (int s = 0; s < 16; s++) {
            if (s < 5) { if (s != 2 && s != 4) mbar_wait_sl(bar_done + (28 + s) * 8, par); }
            else if (s != 14) mbar_wait_sl(bar_done + (27 + s - (s == 15)) * 8, par);
            const uint32_t fb = bar_full + (32 + s) * 8;
            mbar_expect_tx(fb, SLOT);
            tma_load_2d_mc(sbase + rank * 8192 + (uint32_t)((WO_BSLOT >> (4 * s)) & 15) * SLOT, two, fb, jj * 128 + (int)rank * 64, wslice(jj, s) * 64);
            const int ts = s + par;
            if (s >= 5 && ts < 8) {
              mbar_expect_tx(bar_chk - 8 + ts * 8, SLOT);
              tma_load_2d(sbase + (uint32_t)((WO_ASLOT(par) >> (4 * ts)) & 15) * SLOT, &tm_o, bar_chk - 8 + ts * 8, wslice(jj, ts) * 64, mm * 128);
            }
          }
        }
      }
      __syncwarp();
    } else if (warp == 9) {
      const bool el = elect_one();
      if (el) {
        if (!EARLY) { PROFT(472); tma_load_2d(sbase + OFF_S, &tm_x0, bar_full, jj * 128, mm * 128); }
        if (EARLY < 2) { __nanosleep(STAG1); tma_load_2d(sbase + OFF_S + SLOT, &tm_x0, bar_full + 8, jj * 128 + 64, mm * 128); }
      }
      __syncwarp();
      LOAD_EPOCH();
#pragma unroll 1
      for (int lp = 0; lp < 4 * NLAYERS; lp++) {
        const int l = lp >> 2, ph = lp & 3;
        if (ph == 3) continue;
        const uint32_t par = l & 1;
        const unsigned* pp = reinterpret_cast<const unsigned*>(g_obuf + (ph >> 1) * 64 + (size_t)(mm * 128 + (ph ? 0 : S_LEN) + (lane & 7) * 16 + (jj & 1) * 8) * D_MODEL +
                                                               (jj >> 1) * 16 + srcb(jj, lane >> 3) * 128);
        const CUtensorMap* tm = lp ? &tm_o : &tm_x0;
        const int row = mm * 128 + ((ph || !l) ? 0 : S_LEN);
        const uint32_t bit = ph ? O_BIT(l) : X_BIT(l - 1);
        const uint32_t slots = ph ? (uint32_t)(WO_ASLOT(par) >> (ph * 32 - 28)) : 0x8769876u;
        const unsigned long long fr = ph == 0 ? XPACE : ph == 1 ? (par ? 0x353535351Full : 0x35351F1Eull) : (par ? 0x27262524232232ull : 0x27262524233232ull);
        uint32_t no = (lp == 0 || (lp & 7) == 1) ? 0 : ~0u, v0 = 0, v1 = 0;
        if (lp || !AX) mbar_wait_sl(ph ? bar_done + ((uint32_t)fr & 63) * 8 : (l ? bar_done + 47 * 8 : bar_full), ph ? par : (l ? par ^ 1 : 0));
        if (el && ph) PROFT(324 + l * 16 + ph);
        __syncwarp();
        if (no) { v0 = ld_relaxed(pp); __nanosleep(POLLGAP); v1 = ld_relaxed(pp); }
#pragma unroll 1
        for (int i = 0; i < (ph == 1 ? 4 + par : 7); i++, no >>= 8) {
#pragma unroll 1
          for (int it = 0; (no & 0xFF) && it < (1 << 18); it++) {
            no &= __ballot_sync(0xffffffffu, (v0 ^ bit) & 1) >> (8 * i);
            if (no) v0 = ld_relaxed(pp);
            if (!(no & 0xFF)) break;
            no &= __ballot_sync(0xffffffffu, (v1 ^ bit) & 1) >> (8 * i);
            if (no) v1 = ld_relaxed(pp);
          }
          if (ph || i >= XP0) mbar_wait_sl(bar_done + ((uint32_t)(fr >> (8 * i)) & 63) * 8, par);
          if (el) {
            if (i == 0) PROFT(320 + l * 16 + ph);
            const uint32_t cb = bar_chk + (ph >> 1) * 112 + i * 8;
            mbar_expect_tx(cb, SLOT);
            tma_load_2d(sbase + ((slots >> (4 * i)) & 15) * SLOT, tm, cb, srcb(jj, i) * 128 + (ph >> 1) * 64, row);
          }
          __syncwarp();
        }
        if (ph == 0 && el) {
          if (l) { wait_flag(&g_flags.xready[l][mm].v, ep1 * 8); fence_proxy_async_global(); }
#pragma unroll 1
          for (int u = 11; u < 34; u++) {
            if (u == 18) u = 22;
            mbar_wait_sl(bar_done + (u - 4) * 8, par);
            if (u == 32) mbar_expect_tx(bar_xr, 2 * SLOT);
            tma_load_2d(sbase + OFF_RA + (u & 3) * SLOT, tm, u < 32 ? bar_full + u * 8 : bar_xr, kslice(jj, u < 18 ? u - 2 : (u < 32 ? u - 20 : u - 32)) * 64, row);
          }
        }
        __syncwarp();
      }
      if (el && atomicAdd(&g_flags.done.v, 1) == ep1 * NMAIN - 1) asm volatile("st.relaxed.gpu.global.u32 [%0], %1;" :: "l"(&g_flags.epoch.v), "r"(ep1) : "memory");
      __syncwarp();
      cluster_wait();
    } else {
      const int hw = warp - 10;
      LOAD_EPOCH();
      const bool el = elect_one();
      cluster_wait();
      if (hw == 0) {
        mbar_wait_sl(bar_full + 8, 0);
        if (lane < 7) prefetch_tmap(lane == 0 ? &tm_os : lane == 1 ? &tm_o : lane == 2 ? &tm_wf : lane == 3 ? &tm_wqB : lane == 4 ? &tm_woA : lane == 5 ? &tm_woB : &tm_phi);
#pragma unroll 1
        for (int i = 0; i < (NLAYERS > 1 ? 9 : 0); i++) {
          if (i == 0 || i == 5) mbar_wait_sl(bar_done + (i >> 1) * 12, 0);
          if (el) {
            if (i == 0) { mbar_expect_tx(bar_phi, 2 * SLOT + 8192); tma_load_2d(sbase + OFF_PHI, &tm_phi, bar_phi, 0, jj * 128); }
            else tma_load_2d(sbase + (i > 4 ? 10 : 12) * SLOT - 4096 + i * 4096, &tm_wqB, bar_phi, (i > 4 ? 896 : 0) + jj * 128 + ((i - 1) >> 1) * 64, mm * 64 + (~i & 1) * 32);
          }
          __syncwarp();
          __nanosleep(PFGAP);
        }
      } else {
#pragma unroll 1
        for (int b = 0; b < 2; b++) {
          float4* z = reinterpret_cast<float4*>(g_kv[b] + (jj * 4) * KVH + mm * (4 * KVH / 16)) + lane;
#pragma unroll
          for (int i = 0; i < 6; i++) z[i * 32] = make_float4(0.f, 0.f, 0.f, 0.f);
        }
#pragma unroll 1
        for (int i = 0; i < 16; i++) {
          const int b = i >> 2;
          const uint32_t v = (b == 0 ? O_BIT(0) : b == 1 ? X_BIT(0) : H_BIT(0)) + 1;
          uint4* p = b < 2 ? reinterpret_cast<uint4*>(g_obuf + (size_t)(b * S_LEN + mm * 128 + (i & 3) * 32 + (lane >> 3) * 8) * D_MODEL + jj * 128 + (b ? 0 : 64)) + (lane & 7)
                           : g_halo + (size_t)(mm * 8 + jj) * 512 + i * 32 + lane;
          *p = make_uint4(v, v, v, v);
        }
        fence_proxy_async_global();
      }
      __syncwarp();
      uint32_t chkp = 0;
#pragma unroll 1
      for (int lp = 0; lp < 4 * NLAYERS; lp++) {
        const int l = lp >> 2, ph = (lp & 3) == 2 ? 2 - hw : (lp & 3);
        const uint32_t par = l & 1;
        int lane; asm volatile("mov.u32 %0, %%laneid;" : "=r"(lane));
        if ((lp & 3) == 2 || (hw && ph == 0)) {
          const uint32_t bit = ph ? O_BIT(l) : X_BIT(l - 1);
          uint32_t slots = ph ? (uint32_t)(WO_ASLOT(par) >> (ph * 32 - 28)) : 0x8769876u;
          const uint32_t a0 = sbase + (lane & 7) * 132 + (lane >> 3) * 32;
#pragma unroll 1
          for (int c = 0; c < 7; c++, slots >>= 4) {
            const uint32_t cb = bar_chk + 112 - hw * 112 + c * 8;
#pragma unroll 1
            for (int it = 0; it < (1 << 12); it++) {
              mbar_wait_sl(cb, (chkp >> c) & 1);
              chkp ^= 1u << c;
              if (el && c == 0) PROFT(ph == 1 ? 480 + l * 2 : 488 + l * 2 + (ph >> 1));
              if (lp == 0) break;
              uint32_t bad;
              asm volatile("{\n.reg .b32 w<16>;\n"
                           "ld.shared.u32 w0, [%1 + 0];\n"
                           "ld.shared.u32 w1, [%1 + 1024];\n"
                           "ld.shared.u32 w2, [%1 + 2048];\n"
                           "ld.shared.u32 w3, [%1 + 3072];\n"
                           "ld.shared.u32 w4, [%1 + 4096];\n"
                           "ld.shared.u32 w5, [%1 + 5120];\n"
                           "ld.shared.u32 w6, [%1 + 6144];\n"
                           "ld.shared.u32 w7, [%1 + 7168];\n"
                           "ld.shared.u32 w8, [%1 + 8192];\n"
                           "ld.shared.u32 w9, [%1 + 9216];\n"
                           "ld.shared.u32 w10, [%1 + 10240];\n"
                           "ld.shared.u32 w11, [%1 + 11264];\n"
                           "ld.shared.u32 w12, [%1 + 12288];\n"
                           "ld.shared.u32 w13, [%1 + 13312];\n"
                           "ld.shared.u32 w14, [%1 + 14336];\n"
                           "ld.shared.u32 w15, [%1 + 15360];\n"
                           "lop3.b32 w0, w0, w1, %2, 0x7E;\n"
                           "lop3.b32 w2, w2, w3, %2, 0x7E;\n"
                           "lop3.b32 w4, w4, w5, %2, 0x7E;\n"
                           "lop3.b32 w6, w6, w7, %2, 0x7E;\n"
                           "lop3.b32 w8, w8, w9, %2, 0x7E;\n"
                           "lop3.b32 w10, w10, w11, %2, 0x7E;\n"
                           "lop3.b32 w12, w12, w13, %2, 0x7E;\n"
                           "lop3.b32 w14, w14, w15, %2, 0x7E;\n"
                           "lop3.b32 w0, w0, w2, w4, 0xFE;\nlop3.b32 w6, w6, w8, w10, 0xFE;\nlop3.b32 w0, w0, w12, w14, 0xFE;\nlop3.b32 %0, w0, w6, 1, 0xA8;\n}\n"
                           : "=r"(bad) : "r"(a0 + (slots & 15) * SLOT), "r"(bit) : "memory");
              if (__all_sync(0xffffffffu, bad == 0)) break;
              if (el) {
                fence_proxy_async_smem();
                mbar_expect_tx(cb, SLOT);
                tma_load_2d(sbase + (slots & 15) * SLOT, &tm_o, cb, srcb(jj, c) * 128 + (ph >> 1) * 64, mm * 128 + (ph ? 0 : S_LEN));
                RETRY_COUNT();
              }
              __syncwarp();
            }
            if (el) { mbar_arrive_local(bar_full + (c + (ph ? 25 + ph * 8 : 4)) * 8); if (lp == PRL * 4 && c == 0) PROFT(477); }
            __syncwarp();
          }
          if (ph) continue;
#pragma unroll 1
          for (int hp = 0; hp < 2; hp++) {
            const uint4* src = reinterpret_cast<const uint4*>(g_colsum[par][jj * 64 + hp * 32 + lane]);
            uint32_t bad;
            int it = 0;
            float c[6];
            do {
              bad = 0;
#pragma unroll
              for (int p = 0; p < 3; p++) {
                const uint4 v = ld_ll(src + ((par && p < 2) ? (hp ? -32 : 512) + p * 32 : p * 512));
                bad |= (v.y ^ ep1) | (v.w ^ ep1);
                c[2 * p] = __uint_as_float(v.x) + __uint_as_float(v.z); c[2 * p + 1] = __uint_as_float(v.y) + __uint_as_float(v.w);
              }
              bad &= 3;
              if (bad) __nanosleep(300);
            } while (bad && ++it < (1 << 16));
#pragma unroll
            for (int p = 0; p < 6; p++) {
              uint32_t h, m, lo;
              split3(c[p], h, m, lo);
              sts128(sbase + OFF_LNB + hp * 4096 + (p >> 1) * 1024 + lane * 32 + (p & 1) * 16, h | (m << 16), h | (lo << 16), h | (m << 16), lo | (m << 16));
            }
            fence_proxy_async_smem();
            __syncwarp();
            if (el) { mbar_arrive_local(hp ? bar_stat2 : bar_stat); if (hp == 0) PROFT(324 + l * 16); }
            __syncwarp();
          }
          continue;
        } else if (ph == 0) {
          mbar_wait_sl(bar_done + 24, par);
          const uint4* sp = reinterpret_cast<const uint4*>(g_stats + (size_t)(mm * 128) * 8) + lane;
#pragma unroll 1
          for (int hf = 0; hf < 4; hf++) {
            uint4 v[4];
            uint32_t bad;
            int it = 0;
            do {
              bad = 0;
#pragma unroll
              for (int i = 0; i < 4; i++) { v[i] = ld_ll(sp + (hf * 4 + i) * 32); bad |= (v[i].y ^ STAT_TAG(l)) | (v[i].w ^ STAT_TAG(l)); }
              bad &= 3;
              if (bad) __nanosleep(200);
            } while (bad && ++it < (1 << 16));
            __syncwarp();
            float mean = 0.f, m2 = 0.f;
#pragma unroll
            for (int i = 0; i < 4; i++) {
              float a = __uint_as_float(v[i].x) + __uint_as_float(v[i].z);
              a += __shfl_xor_sync(0xffffffffu, a, 1); a += __shfl_xor_sync(0xffffffffu, a, 2);
              a *= 0.125f;
              const float e0 = __uint_as_float(v[i].x) - a, e1 = __uint_as_float(v[i].z) - a;
              float q = fmaf(fmaf(e0, e0, e1 * e1), 128.f, __uint_as_float(v[i].y) + __uint_as_float(v[i].w));
              q += __shfl_xor_sync(0xffffffffu, q, 1); q += __shfl_xor_sync(0xffffffffu, q, 2);
              if ((lane & 3) == i) { mean = a; m2 = q; }
            }
            const uint32_t row = hf * 32 + (lane & 3) * 8 + (lane >> 2);
            uint32_t h, m, lo;
            split3(-0.5f * mean, h, m, lo);
            sts128(sbase + OFF_LNA + row * 16, h | (h << 16), m | (h << 16), lo | (m << 16), m | (lo << 16));
            sts32f(sbase + OFF_ST + row * 4, rsqrtf(m2 * (1.f / 1024.f) + 1e-5f));
          }
          fence_proxy_async_smem();
          __syncwarp();
          if (el) { mbar_arrive_local(bar_stat); PROFT(323 + l * 16); }
          __syncwarp();
#pragma unroll 1
          for (int i = 0; i < 8 - 4 * l; i++) {
            asm volatile("prefetch.global.L2 [%0];" :: "l"(i < 4 ? (l ? prm.wB_o : prm.wA_o) + (size_t)cta * 8192 + i * 2048 + lane * 64
                                                                 : prm.wB_qkv + (size_t)(cta * 8 + (i - 4) * 2 + (lane >> 4)) * 3072 + 2048 + (lane & 15) * 64));
            __nanosleep(PFGAP);
          }
          continue;
        }
        if (ph == 1) {
          if (par) continue;
#pragma unroll 1
          for (int i = 0; i < 2; i++) {
            if (i && lp + hw == 1 && NLAYERS > 1) {
#pragma unroll 1
              for (int c = 0; c < 8; c++) {
                if (!(c & 3)) asm volatile("bar.sync %0, 288;" :: "r"(BAR_WF + (c >> 2)) : "memory");
                if (el) {
                  tma_store_2d(&tm_wf, sbase + 11 * SLOT + c * 4096, (c < 4 ? 1024 : -128) + jj * 128 + (c >> 1) * 64, mm * 64 + (c & 1) * 32);
                  if ((c & 3) == 3) {
                    asm volatile("cp.async.bulk.commit_group;\ncp.async.bulk.wait_group.read 0;" ::: "memory");
                    mbar_arrive_local(bar_phi + (c >> 2) * 8);
                  } else __nanosleep(WFGAP);
                }
                __syncwarp();
              }
              if (el) { bulk_commit_wait(); signal_release(&g_flags.wfready[jj].v); PROFT(335); }
              __syncwarp();
            }
            mbar_wait_sl(bar_done + (i ? HW1 : (hw ? 19 : HW0)) * 8, 0);
            if (lp + hw == 2 && NLAYERS > 1) mbar_wait_sl(bar_phi, 1);
            const uint4* src = g_halo + (size_t)(mm * 8 + jj - 8) * 512 + i * 256 + hw * 128 + lane;
            uint4 v[4];
            int it = 0;
            bool ok;
            do {
#pragma unroll
              for (int j = 0; j < 4; j++) v[j] = mm ? ld_b128(src + j * 32) : make_uint4(H_BIT(l), 0, 0, 0);
              ok = __all_sync(0xffffffffu, (((v[0].x ^ H_BIT(l)) | (v[1].x ^ H_BIT(l)) | (v[2].x ^ H_BIT(l)) | (v[3].x ^ H_BIT(l))) & 1) == 0);
            } while (!ok && ++it < (1 << 16));
#pragma unroll
            for (int j = 0; j < 4; j++) sts128(sbase + OFF_S + hw * SLOT + j * 512 + lane * 16, v[j].x, v[j].y, v[j].z, v[j].w);
            __syncwarp();
            if (el) { mbar_arrive_local(bar_halo + hw * 8); PROFT(331 + l * 16 + i * 2 + hw); }
            __syncwarp();
          }
        } else if (hw == 0 && l < NLAYERS - 1) {
          bar_sync<BAR_X1, 288>();
          if (el) {
            PROFT(328 + l * 16);
            mbar_wait_sl(bar_full + XD * 8, par ^ 1);
            tma_store_2d(&tm_o, sbase + 11 * SLOT, jj * 128 + 64, mm * 128 + S_LEN);
            bulk_commit_wait();
            signal_release(&g_flags.xready[l + 1][mm].v);
            PROFT(330 + l * 16);
          }
          __syncwarp();
        }
      }
    }
    cluster_sync();
  } else {
    asm volatile("setmaxnreg.inc.sync.aligned.u32 232;");
    LOAD_EPOCH();
    const int wg = warp >> 2;
    const int r0 = warp * 16;
    const uint32_t pK = sbase + OFF_S, pV = sbase + OFF_S + SLOT;
#define PMASKS(on, bit) const uint32_t pm0 = ((on) && t == (g & 3) && (g >> 2) == (g & 1)), pm1 = ((on) && t == (g & 3) && (g >> 2) != (g & 1)), pbit = (bit)
#define PBIT0(w) (((w) & ~pm0) | (pbit & pm0))
#define PBIT1(w) (((w) & ~pm1) | (pbit & pm1))
#define LANE_CONSTS() \
    int lane; asm volatile("mov.u32 %0, %%laneid;" : "=r"(lane)); \
    const int g = lane >> 2, t = lane & 3; \
    const uint32_t srowoff = (r0 + (lane & 15)) * 128, lsw = (lane & 7) << 4, lhi = (lane >> 4) << 4, lsw2 = (lane & 6) << 3; \
    (void)g; (void)t; (void)srowoff; (void)lsw; (void)lhi; (void)lsw2;
    uint32_t stgp = 0, peer;
    asm volatile("mapa.shared::cluster.u32 %0, %1, %2;" : "=r"(peer) : "r"(sbase), "r"(rank ^ 1));
    peer -= sbase;
    const uint32_t dA0 = (((sbase & 0x3FFFF) + wg * 8192) >> 4) | 0x10000u, dB0 = ((sbase & 0x3FFFF) >> 4) | 0x2000000u;
    cluster_wait();
#define DESC(lo, hi) ((uint64_t)(uint32_t)(lo) | ((uint64_t)(hi) << 32))
#define STG_ARRIVE() { __syncwarp(); if (elect_one()) mbar_arrive_local(bar_stg); }
#define STG_WAIT() { mbar_wait(bar_stg, stgp); stgp ^= 1; }
#define PROFS() do {} while (0)
#define REL(addr) { if (elect_one()) { mbar_arrive_local(addr); asm volatile("mbarrier.arrive.shared::cluster.b64 _, [%0];" :: "r"((addr) + peer) : "memory"); } }
#define QSTEP(ACC, DA, SC, PRE) { \
      const uint32_t da = (DA), db = dB0 + (ub & 0x18) * (QST >> 7); \
      mbar_wait(ub, par); \
      PRE; \
      wgmma_fence(); \
      wgmma4_n192<SC>(ACC, da, db); \
      wgmma_commit(); PROFS(); }
#define QREL() { wgmma_wait<1>(); REL(ub + 376); ub += 8; }
#define RA_CUR (dA0 + (OFF_RA >> 4) + (ub & 0x18) * (SLOT >> 7))
#define PUMP1() { QSTEP(S1, RA_CUR, 1, {}); QREL(); }
#define PUMP0() { PUMP1(); SCHED_FENCE(); }
#define PUMP() if (h == 0) PUMP1()
#define WSTEP() { \
      const uint32_t s4 = (ub - bar_full - 256) >> 1; \
      const uint32_t da = dA0 + (((uint32_t)(WO_ASLOT(par) >> s4) & 15) << 10), db = dB0 + (((uint32_t)(WO_BSLOT >> s4) & 15) << 10); \
      mbar_wait(ub, par); \
      wgmma_fence(); \
      wgmma4_n128<1>(S1, da, db); \
      wgmma_commit(); PROFS(); \
      wgmma_wait<1>(); \
      if (s4) REL(ub + 376); \
      ub += 8; }
#define PUMPS(n) { _Pragma("unroll 1") for (int i_ = 0; i_ < (n); i_++) PUMP1(); }
#define SITE(n) { if ((BMASK >> (n)) & 1) PUMP1(); SCHED_FENCE(); }
#define LNSTEP(ACC, hh) { wgmma_fence(); wgmma_n192<1, 0>(ACC, make_desc(sbase + OFF_LNA + wg * 1024, 0, 128) ^ (1ull << 62), make_desc(sbase + OFF_LNB + (hh) * 4096, 0, 128) ^ (1ull << 62)); }
#define WARP_STORE(tm, tile, col, row) { fence_proxy_async_smem(); __syncwarp(); \
      if (elect_one()) { tma_store_2d(tm, (tile) + r0 * 128, col, (row) + r0); asm volatile("cp.async.bulk.commit_group;" ::: "memory"); } __syncwarp(); }
#define PUBLISH_O() WARP_STORE(&tm_os, pO, jj * 128 + h * 64, mm * 128)
#define TILE_CONSTS(base, on, bit) \
      uint32_t ta[6]; \
      { PMASKS(on, bit); (void)pbit; ta[4] = pm0; ta[5] = pm1; } \
      _Pragma("unroll") for (int j = 0; j < 4; j++) ta[j] = (base) + srowoff + ((((uint32_t)j << 5) + lhi) ^ lsw); \
      PINU(ta, 6); SCHED_FENCE(); \
      const uint32_t pm0 = ta[4], pm1 = ta[5], pbit = (bit)
#define X_OUT(pc) { \
      _Pragma("unroll") for (int j = (pc) * 4; j < (pc) * 4 + 4; j++) \
        stsm_x4(ta[j & 3] + (pc) * SLOT, \
                PBIT0(pack_bf16(S1[j * 8 + 0], S1[j * 8 + 1])), PBIT0(pack_bf16(S1[j * 8 + 2], S1[j * 8 + 3])), \
                PBIT1(pack_bf16(S1[j * 8 + 4], S1[j * 8 + 5])), PBIT1(pack_bf16(S1[j * 8 + 6], S1[j * 8 + 7]))); }
#define REST_P1(SKEW) { \
      mbar_wait(bar_stat2, par); \
      LNSTEP(S1, 1); \
      _Pragma("unroll 1") while (ub < bar_full + 256) { \
        if (ub == bar_full + 256 - 8 * (SKEW) && wg == 0) bar_sync<BAR_SKEW, 256>(); \
        QSTEP(S1, RA_CUR, 1, {}); \
        if (ub == bar_full + 248 && wg == 1) bar_arrive<BAR_SKEW, 256>(); \
        QREL(); \
      } \
      mbar_wait(bar_done + (31 - (SKEW)) * 8, par);        \
      wgmma_wait<0>(); \
      ACC_FENCE(S1, 96); \
      REL(bar_done + 31 * 8); \
      PROF(13); }
#define FOLD(tile, rd) { \
          LANE_CONSTS(); \
          float d[32]; \
          ACC_DEF(d, 32); \
          mbar_wait(bar_phi, 0); \
          wgmma_fence(); \
          _Pragma("unroll") for (int i = 0; i < 2; i++) { \
            const uint64_t da = make_desc((tile) + wg * 8192 + i * 64, 16, 1024); \
            const uint64_t db = make_desc(sbase + OFF_PHI + wg * 4096 + i * 2048, 16, 512) ^ (3ull << 62); \
            wgmma_n32<0>(d + i * 16, da, db); wgmma_n32<1>(d + i * 16, da + 2, db + 64); \
          } \
          wgmma_commit(); \
          PUMP0(); \
          ACC_FENCE(d, 32); \
          bar_wg(wg); \
          _Pragma("unroll") for (int i = 0; i < 4; i++) { \
            const float* x = d + (i & 1) * 8 + (i >> 1) * 2; \
            if (rd) sts128((tile) + wg * 8192 + ((warp & 3) * 16 + (i >> 1) * 8 + g) * 128 + (((2 * t + (i & 1)) ^ g) << 4), \
                           pack_bf16(x[0], x[1]), pack_bf16(x[4], x[5]), pack_bf16(x[16], x[17]), pack_bf16(x[20], x[21])); \
            else stsm_x4((tile) + srowoff + ((((uint32_t)i << 5) + lhi) ^ lsw), pack_bf16(d[i * 8], d[i * 8 + 1]), pack_bf16(d[i * 8 + 2], d[i * 8 + 3]), \
                         pack_bf16(d[i * 8 + 4], d[i * 8 + 5]), pack_bf16(d[i * 8 + 6], d[i * 8 + 7])); \
          } \
          }
#define LOAD_X0(base) \
      _Pragma("unroll") for (int j = 0; j < 8; j++) { \
        uint32_t x0, x1, x2, x3; \
        ldsm_x4((base) + (j >> 2) * SLOT + srowoff + ((((uint32_t)(j & 3) << 5) + lhi) ^ lsw), x0, x1, x2, x3); \
        S1[j * 8 + 0] = bf_lo(x0); S1[j * 8 + 1] = bf_hi(x0); S1[j * 8 + 2] = bf_lo(x1); S1[j * 8 + 3] = bf_hi(x1); \
        S1[j * 8 + 4] = bf_lo(x2); S1[j * 8 + 5] = bf_hi(x2); S1[j * 8 + 6] = bf_lo(x3); S1[j * 8 + 7] = bf_hi(x3); \
      }
#define LOAD_X() { \
      wgmma_wait<0>(); \
      mbar_wait(bar_xr, par); \
      LOAD_X0(sbase + OFF_RA); \
      ACC_FENCE(S1, 64); \
      __syncwarp(); if (elect_one()) mbar_arrive_local(bar_lx); }

    float S1[96];
#pragma unroll
    for (int i = 0; i < 64; i++) S1[i] = 0.f;
#pragma unroll 1
    for (int l = 0; l < NLAYERS; l++) {
      const uint32_t par = l & 1;
      bar_wg(wg);
      PROF(0);
      uint32_t ub = bar_full;
      float S0[96];
      {
        LANE_CONSTS();
        ACC_DEF(S0, 96);
        QSTEP(S0, dA0 + (OFF_S >> 4), 0, {});
        ub += 8;
        PROF(1);
        if (l == 0) { mbar_wait(ub, 0); LOAD_X0(pK); }
        else { uint32_t ta[4]; for (int j = 0; j < 4; j++) ta[j] = pK + srowoff + ((((uint32_t)j << 5) + lhi) ^ lsw); PMASKS(false, 0); X_OUT(1); fence_proxy_async_smem(); }
        SCHED_FENCE();
        {
          float a0 = S1[0], a1 = S1[2], b0 = S1[1], b1 = S1[3];
#pragma unroll
          for (int i = 4; i < 64; i += 4) { a0 += S1[i]; b0 += S1[i + 1]; a1 += S1[i + 2]; b1 += S1[i + 3]; }
          a0 += b0; a1 += b1;
          a0 += __shfl_xor_sync(0xffffffffu, a0, 1); a1 += __shfl_xor_sync(0xffffffffu, a1, 1);
          a0 += __shfl_xor_sync(0xffffffffu, a0, 2); a1 += __shfl_xor_sync(0xffffffffu, a1, 2);
          a0 *= (1.f / 128.f); a1 *= (1.f / 128.f);
          asm volatile("" : "+f"(a0), "+f"(a1));
          bar_wg(wg);
          QSTEP(S0, dA0 + ((OFF_S + SLOT) >> 4), 1, wgmma_wait<0>());
          REL(ub + 376); ub += 8;
          SCHED_FENCE();
          float q0 = 0.f, q1 = 0.f;
          b0 = 0.f; b1 = 0.f;
#pragma unroll
          for (int i = 0; i < 64; i += 4) {
            const float d0 = S1[i] - a0, d1 = S1[i + 1] - a0, d2 = S1[i + 2] - a1, d3 = S1[i + 3] - a1;
            q0 = fmaf(d0, d0, q0); b0 = fmaf(d1, d1, b0); q1 = fmaf(d2, d2, q1); b1 = fmaf(d3, d3, b1);
          }
          q0 += b0; q1 += b1;
          q0 += __shfl_xor_sync(0xffffffffu, q0, 1); q1 += __shfl_xor_sync(0xffffffffu, q1, 1);
          q0 += __shfl_xor_sync(0xffffffffu, q0, 2); q1 += __shfl_xor_sync(0xffffffffu, q1, 2);
          if (t < 2) st_b64(g_stats + (size_t)(mm * 128 + r0 + g + t * 8) * 8 + jj, __float_as_uint(t ? a1 : a0), (__float_as_uint(t ? q1 : q0) & ~3u) | STAT_TAG(l));
        }
        if (l) { asm volatile("cp.async.bulk.wait_group 0;" ::: "memory"); bar_arrive<BAR_X1, 288>(); }
        ACC_DEF(S1, 96);
        QSTEP(S1, dA0 + (OFF_S >> 4), 0, {});
        QREL();
        QSTEP(S1, dA0 + ((OFF_S + SLOT) >> 4), 1, {});
        QREL();
#pragma unroll 1
        for (int i = 0; i < 14; i++) {
          QSTEP(S0, RA_CUR, 1, {});
          if (i == 0) PROF(2);
          QREL();
        }
      }
      LANE_CONSTS();
      mbar_wait(bar_stat, par);
      LNSTEP(S0, 0);
      wgmma_commit();
      const float rs0 = lds32f(sbase + OFF_ST + (r0 + g) * 4), rs1 = lds32f(sbase + OFF_ST + (r0 + g + 8) * 4);
      PUMP0();
      ACC_FENCE(S0, 96);
      PROF(3);
      if (!par) {
        constexpr uint32_t par = 0;
        uint32_t qa[16];
        uint32_t kf[32], vf[32];
#define DRAIN_A(ACC, hp, PMP) { \
          LANE_CONSTS(); \
          FRAG(kf + 16, ACC + 32, 0, (hp) * 2); \
          PMP; \
          FRAG(vf + 16, ACC + 64, 1, (hp) * 2 + 1); \
          _Pragma("unroll") for (int i_ = 0; i_ < 16; i_++) qa[i_] = pack_bf16(ACC[2 * i_], ACC[2 * i_ + 1]); \
          PINU(qa, 16); }
        DRAIN_A(S0, 0, PUMP0());
        if (l == 0 && NLAYERS > 1) {
#pragma unroll 1
          for (int rd = 1; rd >= 0; rd--) {
            FOLD(sbase + (12 - rd) * SLOT, rd);
            fence_proxy_async_smem();
            asm volatile("bar.arrive %0, 288;" :: "r"(BAR_WF + 1 - rd) : "memory");
          }
        }
        PUMPS(FPUMP);
        if (l == 0 && NLAYERS > 1) mbar_wait(bar_phi, 1);
#pragma unroll 1
        for (int h = 0; h < 2; h++) {
          const uint32_t pO = sbase + (h ? 3 : 12) * SLOT;
          PROF(4 + h * 12);
          LANE_CONSTS();
          FRAG_PUT(kf + 16, 10); FRAG_PUT(vf + 16, 11);
          STG_ARRIVE();
          if (h) { LOAD_X(); if (AW0) WSTEP(); } else PUMPS(HPUMP2);
          const bool e = g & 1, hb = (2 * t + (g & 1)) <= g;
          uint32_t sel[3] = {e ? 0x1044u : 0x4410u, hb ? 0x4444u : (e ? 0x3244u : 0x4432u), hb ? (e ? 0x3244u : 0x4432u) : 0x4444u};
          PINU(sel, 3);
          TILE_CONSTS(pO, true, O_BIT(l));
          const uint32_t selA = sel[0], selL = sel[1], selH = sel[2];
          STG_WAIT();
          if (warp == 0) mbar_wait(bar_halo, h);
          FRAG_GET(kf, 10);
          PROF(5 + h * 12);
          float s[2][4][4];
#pragma unroll
          for (int ks = 0; ks < 2; ks++)
#pragma unroll
            for (int i = 0; i < 8; i++) {
              const int hh = (i >> 1) & 1, jb = (i & 1) + (~i >> 1 & 2);
              const uint32_t* b = kf + (jb >> 1) * 16 + hh * 8 + ks * 4 + (jb & 1) * 2;
              if (ks) mma_bf16(s[hh][jb], qa[hh * 8 + 4], qa[hh * 8 + 5], qa[hh * 8 + 6], qa[hh * 8 + 7], b[0], b[1]);
              else mma_bf16_z(s[hh][jb], qa[hh * 8], qa[hh * 8 + 1], qa[hh * 8 + 2], qa[hh * 8 + 3], b[0], b[1]);
            }
          PUMP();
          PROF(6 + h * 12);
          float va[2][2], vb[2][2], mx[2][2];
#pragma unroll
          for (int hh = 0; hh < 2; hh++) {
            va[hh][0] = e ? s[hh][1][1] : s[hh][1][0];
            vb[hh][0] = hb ? (e ? s[hh][2][1] : s[hh][2][0]) : (e ? s[hh][0][1] : s[hh][0][0]);
            va[hh][1] = e ? s[hh][2][3] : s[hh][2][2];
            vb[hh][1] = hb ? (e ? s[hh][3][3] : s[hh][3][2]) : (e ? s[hh][1][3] : s[hh][1][2]);
          }
          if (warp == 0 && mm == 0) {
#pragma unroll
            for (int hh = 0; hh < 2; hh++) { va[hh][0] = -INFINITY; if (!hb) { vb[hh][0] = -INFINITY; vb[hh][1] = -INFINITY; } }
          }
#pragma unroll
          for (int i = 0; i < 4; i++) mx[i >> 1][i & 1] = fmaxf(va[i >> 1][i & 1], vb[i >> 1][i & 1]);
#pragma unroll
          for (int o = 1; o <= 2; o <<= 1)
#pragma unroll
            for (int i = 0; i < 4; i++) mx[i >> 1][i & 1] = fmaxf(mx[i >> 1][i & 1], __shfl_xor_sync(0xffffffffu, mx[i >> 1][i & 1], o));
          const float sc0 = rs0 * (0.17677669529663687f * LOG2E), sc1 = rs1 * (0.17677669529663687f * LOG2E);
#pragma unroll
          for (int i = 0; i < 4; i++) {
            const float sc = (i & 1) ? sc1 : sc0, m = mx[i >> 1][i & 1];
            va[i >> 1][i & 1] = ex2((va[i >> 1][i & 1] - m) * sc); vb[i >> 1][i & 1] = ex2((vb[i >> 1][i & 1] - m) * sc);
            mx[i >> 1][i & 1] = va[i >> 1][i & 1] + vb[i >> 1][i & 1];
          }
          if (h == 0 && ASITE) { PIN(&va[0][0], 4); PIN(&vb[0][0], 4); PIN(&mx[0][0], 4); PUMP1(); }
          if (warp == 0) mbar_wait(bar_halo + 8, h);
          FRAG_GET(vf, 11);
#pragma unroll
          for (int o = 1; o <= 2; o <<= 1)
#pragma unroll
            for (int i = 0; i < 4; i++) mx[i >> 1][i & 1] += __shfl_xor_sync(0xffffffffu, mx[i >> 1][i & 1], o);
          float o[2][4][4];
          uint32_t pa[2][8];
#pragma unroll
          for (int hh = 0; hh < 2; hh++) {
            const float i0 = rcp_fast(mx[hh][0]), i1 = rcp_fast(mx[hh][1]);
            const uint32_t w0 = pack_bf16(va[hh][0] * i0, vb[hh][0] * i0), w1 = pack_bf16(va[hh][1] * i1, vb[hh][1] * i1);
            pa[hh][0] = __byte_perm(w0, 0, selL); pa[hh][2] = __byte_perm(w0, 0, selA); pa[hh][3] = __byte_perm(w1, 0, selL);
            pa[hh][4] = __byte_perm(w0, 0, selH); pa[hh][5] = __byte_perm(w1, 0, selA); pa[hh][7] = __byte_perm(w1, 0, selH);
            pa[hh][1] = pa[hh][0] & pa[hh][4]; pa[hh][6] = pa[hh][3] & pa[hh][7];
          }
          PROF(7 + h * 12);
#pragma unroll
          for (int i = 0; i < 8; i++) mma_bf16_z(o[i >> 2][i & 3], pa[i >> 2][4], pa[i >> 2][5], pa[i >> 2][6], pa[i >> 2][7], vf[16 + 2 * i], vf[17 + 2 * i]);
#pragma unroll
          for (int i = 0; i < 8; i++) mma_bf16(o[i >> 2][i & 3], pa[i >> 2][0], pa[i >> 2][1], pa[i >> 2][2], pa[i >> 2][3], vf[2 * i], vf[2 * i + 1]);
          if (h == 0) PUMP1() else mbar_wait(bar_done + 30 * 8, par);
          if (NLAYERS > 1) mbar_wait(bar_phi + 8, 0);
#pragma unroll
          for (int i = 0; i < 4; i++) {
            const int hh = i >> 1, dp = i & 1;
            stsm_x4(ta[i],
                    PBIT0(pack_bf16(o[hh][dp * 2][0], o[hh][dp * 2][1])), PBIT0(pack_bf16(o[hh][dp * 2][2], o[hh][dp * 2][3])),
                    PBIT1(pack_bf16(o[hh][dp * 2 + 1][0], o[hh][dp * 2 + 1][1])), PBIT1(pack_bf16(o[hh][dp * 2 + 1][2], o[hh][dp * 2 + 1][3])));
          }
          PUBLISH_O();
          PROF(11 + h * 12);
          if (h) break;
          REST_P1(ASKEW);
          asm volatile("cp.async.bulk.wait_group.read 0;" ::: "memory");
          DRAIN_A(S1, 1, {});
        }
      } else {
        constexpr uint32_t par = 1;
        float st[32];
        const float c0 = rs0 * LOG2E, c1 = rs1 * LOG2E;
        { V_ADDR(pV); STAGE_V(S0 + 64); }
        if (warp < 2) sts128(sbase + OFF_ONES + warp * 512 + lane * 16, 0x3F803F80u, 0x3F803F80u, 0x3F803F80u, 0x3F803F80u);
        scale32(st, S0, c0, c1);
        PIN(st, 32);
#define KV_MMA(vs) { \
          const uint32_t dp = dA0 + 12 * 1024 - wg * 2560, dv = dA0 + (vs) * 1024 + ((OFF_ONES - (vs) * SLOT - 16) << 12) - wg * (512 << 16); \
          STG_WAIT(); \
          wgmma_fence(); \
          _Pragma("unroll") for (int ks = 0; ks < 8; ks++) { \
            const uint64_t a = DESC(dp + ks * 128, 0x40000040), b = DESC(dv + ks * (64 - (64 << 16)), 0x80000020); \
            if (ks == 0) wgmma_n40<0, 1>(kv, a, b); else wgmma_n40<1, 1>(kv, a, b); } \
          wgmma_commit(); }
#define KV_RED(hp) { \
          float* kvg = g_kv[l >> 1] + (jj * 4 + (hp) * 2) * KVH + warp * 768 + lane * 4; \
          _Pragma("unroll") for (int i = 0; i < 5; i++) red_v4(kvg + i * 128, kv[i * 3], kv[i * 3 + 1], kv[i * 3 + 2], 1.f); \
          red_v4(kvg + 640, kv[15], kv[16], kv[18], 1.f); }
#define KV_LOAD(hp) { \
          const uint4* kvg = reinterpret_cast<const uint4*>(g_kv[l >> 1] + (jj * 4 + (hp) * 2) * KVH) + warp * 192 + lane; \
          _Pragma("unroll") for (int i = 0; i < 6; i++) v[i] = ld_b128(kvg + i * 32); }
#define KVV(i) __uint_as_float((i) % 3 == 0 ? v[(i) / 3].x : ((i) % 3 == 1 ? v[(i) / 3].y : v[(i) / 3].z))
#define KV_TILE(hp) { \
          _Pragma("unroll 1") for (int it = 0; it < (1 << 16); it++) { \
            if (__all_sync(0xffffffffu, (v[0].w & v[1].w & v[2].w & v[3].w & v[4].w & v[5].w) == 0x41800000u)) break; \
            RETRY_COUNT(); \
            KV_LOAD(hp); \
          } \
          PROF(25 + (hp)); \
          const uint32_t e = lane & 7, jt = ((lane >> 1) & 4) + (e >> 1); \
          const uint32_t row = ((((warp >> 1) ^ wg) & 1) << 5) + ((jt & 1) << 4) + ((warp & 1) << 3) + (jt & 6) + (e & 1); \
          const uint32_t kd = pV + wg * 8192 + row * 128, ksw = (row & 7) << 4; \
          _Pragma("unroll") for (int i = 0; i < 2; i++) \
            stsm_x4(kd + ((i * 32 + lhi) ^ ksw), pack_bf16(KVV(i * 8), KVV(i * 8 + 1)), pack_bf16(KVV(i * 8 + 2), KVV(i * 8 + 3)), \
                    pack_bf16(KVV(i * 8 + 4), KVV(i * 8 + 5)), pack_bf16(KVV(i * 8 + 6), KVV(i * 8 + 7))); \
          stsm_x4(kd + ((64u + lhi) ^ ksw), pack_bf16(KVV(16), 1.f), pack_bf16(KVV(17), 1.f), 0u, 0u); }
#pragma unroll 1
        for (int h = 0; h < 2; h++) {
          PROF(4 + h * 2);
          SITE(0);
          LANE_CONSTS();
          const uint32_t dsw = (uint32_t)(g ^ (2 * t)) << 4, dst = ((t & 2) ? pK : sbase + 12 * SLOT) + (r0 + g) * 128;
          float e[16], f[16];
          float sa = exps16_<0>(e, st);
          exps16_fix<0>(e, st, sa);
          asm volatile("" : "+f"(sa)); PIN(e, 16); SITE(1);
          if (h) STG_WAIT();
          store16(e, sa, dst, dsw, 4);
          float sb = exps16_<1>(f, st);
          exps16_fix<1>(f, st, sb);
          asm volatile("" : "+f"(sb)); PIN(f, 16); SITE(2);
          store16(f, sb, dst, dsw, 0);
          float sc = exps16_<0>(e, st + 2);
          exps16_fix<0>(e, st + 2, sc);
          asm volatile("" : "+f"(sc)); PIN(e, 16); SITE(3);
          store16(e, sc, dst + 1024, dsw, 4);
          float sd = exps16_<1>(f, st + 2);
          exps16_fix<1>(f, st + 2, sd);
          asm volatile("" : "+f"(sd)); PIN(f, 16); SITE(4);
          store16(f, sd, dst + 1024, dsw, 0);
          PROF(5 + h * 2);
          if (h) break;
          {
            float kv[20];
            ACC_DEF(kv, 20);
            fence_proxy_async_smem();
            STG_ARRIVE();
            KV_MMA(11);
            PUMP0();
            ACC_FENCE(kv, 20);
            KV_RED(0);
            STG_ARRIVE();
          }
          scale32(st, S0 + 32, c0, c1);
          PIN(st, 32);
        }
        bool big;
        uint4 v[6];
        {
          float kv[20];
          if (KT0) { LANE_CONSTS(); KV_LOAD(0); }
          mbar_wait(bar_stat2, par);
          LNSTEP(S1, 1);
          ub = bar_full + 240;
          PUMP1();
          if (wg == 0) bar_sync<BAR_SKEW, 256>();
          QSTEP(S1, RA_CUR, 1, {});
          if (wg == 1) bar_arrive<BAR_SKEW, 256>();
          QREL();
          if (KT0 == 2) { LANE_CONSTS(); KV_TILE(0); }
          LANE_CONSTS();
          V_ADDR(sbase + 3 * SLOT);
          PINU(va_, 2);
          mbar_wait(bar_done + 30 * 8, par);
          wgmma_wait<0>();
          ACC_FENCE(S1, 96);
          if (!(RLATE & 2)) REL(bar_done + 31 * 8);
          PROF(13);
          STAGE_V(S1 + 64);
          fence_proxy_async_smem();
          STG_ARRIVE();
          if (RLATE & 2) REL(bar_done + 31 * 8);
          scale32(st, S1, c0, c1);
          PIN(st, 32);
          PROF(16);
          ACC_DEF(kv, 20);
          KV_MMA(3);
          SCHED_FENCE();
          if (!KT0) KV_LOAD(0);
          big = any_big(st);
          if (EROT > 0) { phiq_a(st, big); PIN(st, 16); }
          SCHED_FENCE();
          wgmma_wait<0>();
          ACC_FENCE(kv, 20);
          KV_RED(1);
          PROF(17);
        }
#pragma unroll 1
        for (int h = 0; h < 2; h++) {
          const uint32_t pO = sbase + (h ? 3 : 8) * SLOT;
          LANE_CONSTS();
          uint32_t fq[32];
          if (EROT < 1) phiq_a(st, big);
          if (EMRG == 0) { phiq_b<0>(fq, st, big); PINU(fq, 16); }
          if (EMRG == 2) { phiq_b<1>(fq, st, big); PINU(fq, 16); PIN(st + 16, 16); }
          PROF(18 + h * 14);
          SCHED_FENCE();
          if (h) {
            asm volatile("cp.async.bulk.wait_group.read 0;" ::: "memory");
            mbar_wait(bar_lx, par);
          }
          if (h || KT0 < 2) {
            KV_TILE(h);
            fence_proxy_async_smem();
            STG_ARRIVE();
          }
          SCHED_FENCE();
          if (EMRG == 0) { phiq_a(st + 16, big); PIN(st + 16, 16); }
          if (EMRG == 1) { phiq_b<1>(fq, st, big); PINU(fq, 16); PIN(st + 16, 16); }
          if (h || KT0 < 2) STG_WAIT();
          wgmma_wait<0>();
          ACC_FENCE(S1, 64);
          PROF(19 + h * 14);
          float o[4][20];
#define O_MMA(hh) { \
            const uint64_t db = make_desc(pV + (hh) * 8192, 16, 1024); \
            ACC_DEF(o[(hh) * 2], 20); ACC_DEF(o[(hh) * 2 + 1], 20); \
            wgmma_fence(); \
            wgmma_n40_rs<0>(o[(hh) * 2], fq + (hh) * 16, db + 256); wgmma_n40_rs<0>(o[(hh) * 2 + 1], fq + (hh) * 16 + 8, db); \
            wgmma_n40_rs<1>(o[(hh) * 2], fq + (hh) * 16 + 4, db + 384); wgmma_n40_rs<1>(o[(hh) * 2 + 1], fq + (hh) * 16 + 12, db + 128); \
            wgmma_commit(); }
          O_MMA(0);
          SCHED_FENCE();
          phiq_b<0>(fq + 16, st + 16, big); PINU(fq + 16, 16);
          SCHED_FENCE();
          PMASKS(true, O_BIT(l));
#pragma unroll
          for (int hh = 0; hh < 2; hh++) {
            if (hh && !OW) O_MMA(1);
            wgmma_wait<0>();
            ACC_FENCE(o[hh * 2], 20); ACC_FENCE(o[hh * 2 + 1], 20);
            if (!hh && OW) { O_MMA(1); SCHED_FENCE(); }
            const float* x = o[hh * 2];
            const float* y = o[hh * 2 + 1];
            const float sx0 = x[17] * 0x1p-40f, sy0 = y[17] * 0x1p-40f, sx1 = x[19] * 0x1p-40f, sy1 = y[19] * 0x1p-40f;
            const float i0 = rcp_fast(fmaf(fmaf(x[17], 1e-6f, x[16]), sy0, y[16] * sx0)), i1 = rcp_fast(fmaf(fmaf(x[19], 1e-6f, x[18]), sy1, y[18] * sx1));
            const float ax0 = sy0 * i0, ay0 = sx0 * i0, ax1 = sy1 * i1, ay1 = sx1 * i1;
#pragma unroll
            for (int dp = 0; dp < 2; dp++)
              stsm_x4(pO + srowoff + ((hh * 64 + dp * 32 + lhi) ^ lsw),
                      PBIT0(pack_bf16(fmaf(x[dp * 8], ax0, y[dp * 8] * ay0), fmaf(x[dp * 8 + 1], ax0, y[dp * 8 + 1] * ay0))),
                      PBIT0(pack_bf16(fmaf(x[dp * 8 + 2], ax1, y[dp * 8 + 2] * ay1), fmaf(x[dp * 8 + 3], ax1, y[dp * 8 + 3] * ay1))),
                      PBIT1(pack_bf16(fmaf(x[dp * 8 + 4], ax0, y[dp * 8 + 4] * ay0), fmaf(x[dp * 8 + 5], ax0, y[dp * 8 + 5] * ay0))),
                      PBIT1(pack_bf16(fmaf(x[dp * 8 + 6], ax1, y[dp * 8 + 6] * ay1), fmaf(x[dp * 8 + 7], ax1, y[dp * 8 + 7] * ay1))));
          }
          PUBLISH_O();
          PROF(20 + h * 14);
          if (h) break;
          if (KVL == 2) { KV_LOAD(1); SCHED_FENCE(); }
          scale32(st, S1 + 32, c0, c1);
          PIN(st, 32);
          LOAD_X();
          bar_wg(wg);
          WSTEP();
          SCHED_FENCE();
          if (KVL == 0) KV_LOAD(1);
          big = any_big(st);
          if (KVL == 1) { SCHED_FENCE(); KV_LOAD(1); }
          if (EROT > 0) { phiq_a(st, big); PIN(st, 16); }
          PROF(31);
        }
      }
      __syncwarp();
      if (elect_one()) mbar_arrive_local(bar_epi);
      bar_wg(wg);
#pragma unroll 1
      while (ub < bar_full + 384) {
        WSTEP();
        if (ub == bar_full + 8 * 41) { asm volatile("cp.async.bulk.wait_group.read 0;" ::: "memory"); PROF(35); }
        if (ub == bar_full + 8 * 42) PROF(36);
      }
      {
        LANE_CONSTS();
        TILE_CONSTS(pK, l < NLAYERS - 1, X_BIT(l));
        wgmma_wait<0>();
        ACC_FENCE(S1, 64);
        if (!RLATE) REL(bar_done + 47 * 8);
        PROF(37);
        X_OUT(0);
        WARP_STORE(l < NLAYERS - 1 ? &tm_os : &tm_xo, pK, jj * 128, mm * 128 + (l < NLAYERS - 1 ? S_LEN : 0));
        if (RLATE) REL(bar_done + 47 * 8);
        if (l == NLAYERS - 1) {
          X_OUT(1);
          WARP_STORE(&tm_xo, pV, jj * 128 + 64, mm * 128);
          if (FINW) asm volatile("cp.async.bulk.wait_group 0;" ::: "memory"); else asm volatile("cp.async.bulk.wait_group.read 0;" ::: "memory");
        }
      }
#pragma unroll
      for (int i = 32; i < 64; i++) { uint32_t c; asm volatile("mov.b32 %0, %1;" : "=r"(c) : "f"(S1[i])); S1[i] = __uint_as_float(c); }
      PROF(38);
    }
    cluster_sync();
  }
}

typedef CUresult (*PFN_encode)(CUtensorMap*, CUtensorMapDataType, cuuint32_t, void*, const cuuint64_t*, const cuuint64_t*,
                               const cuuint32_t*, const cuuint32_t*, CUtensorMapInterleave, CUtensorMapSwizzle,
                               CUtensorMapL2promotion, CUtensorMapFloatOOBfill);

CUtensorMap make_map(PFN_encode enc, const void* ptr, uint64_t inner, uint64_t outer, uint32_t box_inner, uint32_t box_outer,
                     CUtensorMapSwizzle swz = CU_TENSOR_MAP_SWIZZLE_128B) {
  CUtensorMap m;
  cuuint64_t dims[2] = {inner, outer};
  cuuint64_t strides[1] = {inner * 2};
  cuuint32_t box[2] = {box_inner, box_outer};
  cuuint32_t es[2] = {1, 1};
  enc(&m, CU_TENSOR_MAP_DATA_TYPE_BFLOAT16, 2, const_cast<void*>(ptr), dims, strides, box, es, CU_TENSOR_MAP_INTERLEAVE_NONE,
      swz, CU_TENSOR_MAP_L2_PROMOTION_L2_256B, CU_TENSOR_MAP_FLOAT_OOB_FILL_NONE);
  return m;
}

}

extern "C" void kernel_launch(void* const* d_in, const int* in_sizes, int n_in, void* d_out, int out_size) {
  (void)in_sizes; (void)n_in; (void)out_size;
  static PFN_encode enc = nullptr;
  if (!enc) {
    void* fn = nullptr;
    cudaDriverEntryPointQueryResult qr;
    cudaGetDriverEntryPoint("cuTensorMapEncodeTiled", &fn, cudaEnableDefault, &qr);
    enc = (PFN_encode)fn;
    cudaFuncSetAttribute(mega_kernel, cudaFuncAttributeMaxDynamicSharedMemorySize, SMEM_BYTES);
  }
  Params prm;
  prm.x0 = (const __nv_bfloat16*)d_in[0];
  prm.wA_qkv = (const __nv_bfloat16*)d_in[1];
  prm.wA_o = (const __nv_bfloat16*)d_in[2];
  prm.wB_qkv = (const __nv_bfloat16*)d_in[4];
  prm.wB_phi = (const __nv_bfloat16*)d_in[5];
  prm.wB_o = (const __nv_bfloat16*)d_in[6];
  prm.out = (__nv_bfloat16*)d_out;
  void *obuf = nullptr, *wf = nullptr;
  cudaGetSymbolAddress(&obuf, g_obuf);
  cudaGetSymbolAddress(&wf, g_wfold);
  CUtensorMap tm_x0 = make_map(enc, d_in[0], D_MODEL, S_LEN, 64, 128);
  CUtensorMap tm_xo = make_map(enc, d_out, D_MODEL, S_LEN, 64, 16);
  CUtensorMap tm_os = make_map(enc, obuf, D_MODEL, 2 * S_LEN, 64, 16);
  CUtensorMap tm_o = make_map(enc, obuf, D_MODEL, 2 * S_LEN, 64, 128);
  CUtensorMap tm_wf = make_map(enc, wf, 2048, D_MODEL, 64, 32);
  CUtensorMap tm_wqA = make_map(enc, d_in[1], 3 * D_MODEL, D_MODEL, 64, 32);
  CUtensorMap tm_wqB = make_map(enc, prm.wB_qkv, 3 * D_MODEL, D_MODEL, 64, 32);
  CUtensorMap tm_woA = make_map(enc, prm.wA_o, D_MODEL, D_MODEL, 64, 64);
  CUtensorMap tm_woB = make_map(enc, prm.wB_o, D_MODEL, D_MODEL, 64, 64);
  CUtensorMap tm_phi = make_map(enc, prm.wB_phi, 32, 1024, 32, 128, CU_TENSOR_MAP_SWIZZLE_64B);
  mega_kernel<<<NMAIN + NAUX, 384, SMEM_BYTES>>>(tm_x0, tm_xo, tm_os, tm_o, tm_wf, tm_wqA, tm_wqB, tm_woA, tm_woB, tm_phi, prm);
}
```

```cpp
#include <cuda_runtime.h>
#include <cuda.h>
#include <cuda_bf16.h>
#include <stdint.h>

#define NLAYERS 4

#define STAG1 0
#define HPUMP1 2
#define HPUMP2 1
#define ASKEW 2
#define FPUMP 3
#define PFGAP 100
#define POLLGAP 120
#define OW 1
#define AW0 1
#define RLATE 3
#define FSTART 0
#define MAPV 1
#define HW1 29
#define XPACE 0x06050401000000ull
#define XP0 4
#define HW0 18
#define XD 4
#define WFGAP 50
#define KT0 2
#define W23 0
#define AX 0
#define PF0 1
#define EARLY 2
#define BIGLIM 3600.f
#define SUMLO 0x1p-100f
#define SUMHI 0x1p100f
#define EROT 1
#define FINW 0
#define AHOIST 1
#define EMRG 1
#define XPROMO 2
#define OPROMO 3
#define STAG2 300
#define WPROMO 3
#define SB0 2
#define SB1 4
#define SB2 6
#define SB3 8
#define KVL 0
#define BMASK 0x1F
#define ASITE 1
namespace {

constexpr int S_LEN = 2048, D_MODEL = 1024;
constexpr int NAUX = 4, NMAIN = 128;
constexpr int SLOT = 16384;
constexpr int QST = 24576;
constexpr int OFF_RA = 6 * SLOT, OFF_S = 10 * SLOT;
constexpr int OFF_HALO = 13 * SLOT, OFF_LNB = OFF_HALO  , OFF_ONES = OFF_HALO + 3072;
constexpr int OFF_ST = OFF_HALO + 7168  , OFF_PHI = OFF_HALO + 8192;
constexpr int OFF_BAR = 14 * SLOT;
constexpr int OFF_LNA = OFF_BAR + 1024;
constexpr int SMEM_BYTES = OFF_LNA + 2048;
#define WO_ASLOT(par) ((par) ? 0x9876CAB39876CA98ull : 0x98C76BA398C7698Cull)
constexpr unsigned long long WO_BSLOT = 0x5432105421054210ull;
__device__ __forceinline__ int srcb(int j, int i) { return (i + (i >= j)) & 7; }
__device__ __forceinline__ int kslice(int j, int i) { return i < 2 ? 2 * j + i : (i < 9 ? 2 * srcb(j, i - 2) : 2 * srcb(j, i - 9) + 1); }
__device__ __forceinline__ int wslice(int j, int s) { return 2 * ((s & 7) ? srcb(j, (s & 7) - 1) : j) + (s >> 3); }
constexpr int KVH = 6 * 128 * 4;

struct __align__(128) Flag { unsigned v; unsigned pad[31]; };
struct Flags {
  Flag xready[4][16];
  Flag wfready[8];
  Flag done;
  Flag epoch;
};

__device__ Flags g_flags;
__device__ __nv_bfloat16 g_obuf[2 * S_LEN * D_MODEL];
#define O_BIT(l) ((epoch * NLAYERS + (l) + 1) & 1u)
#define X_BIT(l) ((epoch * (NLAYERS - 1) + (l) + 1) & 1u)
__device__ __nv_bfloat16 g_wfold[D_MODEL * 2048];
__device__ uint4 g_halo[16 * 8 * 512];
__device__ __align__(128) float g_kv[2][32 * KVH];
__device__ __align__(128) uint2 g_colsum[2][1536][2];
__device__ __align__(128) uint2 g_stats[S_LEN * 8];
#define H_BIT(l) (NLAYERS > 2 ? (uint32_t)((l) == 0) : (ep1 & 1))
#define STAT_TAG(l) ((ep1 * NLAYERS + (l) + 1) & 3u)

#define RETRY_COUNT()
#define PRL 0
#define PRU 0
#define PROFL 1
#define PROFW 0
#define PROFT(i) do {} while (0)
#define PROF(i) do {} while (0)

__device__ __forceinline__ uint32_t smem_u32(const void* p) { return (uint32_t)__cvta_generic_to_shared(p); }
__device__ __forceinline__ bool elect_one() {
  uint32_t p;
  asm volatile("{\n.reg .pred p;\nelect.sync _|p, 0xffffffff;\nselp.u32 %0, 1, 0, p;\n}\n" : "=r"(p));
  return p != 0;
}
__device__ __forceinline__ void mbar_init(uint32_t bar, uint32_t cnt) {
  asm volatile("mbarrier.init.shared::cta.b64 [%0], %1;" :: "r"(bar), "r"(cnt));
}
__device__ __forceinline__ void mbar_expect_tx(uint32_t bar, uint32_t bytes) {
  asm volatile("mbarrier.arrive.expect_tx.shared::cta.b64 _, [%0], %1;" :: "r"(bar), "r"(bytes) : "memory");
}
#define mbar_wait(bar, parity) \
  asm volatile("{\n.reg .pred p, q;\nW_%=:\nmbarrier.try_wait.parity.shared::cta.b64 p, [%1], %2;\nadd.s32 %0, %0, -1;\n" \
               "setp.gt.and.s32 q, %0, 0, !p;\n@q bra.uni W_%=;\n}\n" : "+r"(budget) : "r"((uint32_t)(bar)), "r"((uint32_t)(parity)) : "memory")
#define mbar_wait_sl(bar, parity) \
  asm volatile("{\n.reg .pred p, q;\nW_%=:\nmbarrier.try_wait.parity.shared::cta.b64 p, [%1], %2, 20000;\nadd.s32 %0, %0, -64;\n" \
               "setp.gt.and.s32 q, %0, 0, !p;\n@q bra.uni W_%=;\n}\n" : "+r"(budget) : "r"((uint32_t)(bar)), "r"((uint32_t)(parity)) : "memory")
__device__ __forceinline__ void mbar_arrive_local(uint32_t bar) {
  asm volatile("mbarrier.arrive.shared::cta.b64 _, [%0];" :: "r"(bar) : "memory");
}
__device__ __forceinline__ void tma_load_2d(uint32_t dst, const CUtensorMap* tm, uint32_t bar, int c0, int c1) {
  asm volatile("cp.async.bulk.tensor.2d.shared::cluster.global.mbarrier::complete_tx::bytes [%0], [%1, {%3, %4}], [%2];"
               :: "r"(dst), "l"(tm), "r"(bar), "r"(c0), "r"(c1) : "memory");
}
__device__ __forceinline__ void tma_load_2d_mc(uint32_t dst, const CUtensorMap* tm, uint32_t bar, int c0, int c1) {
  asm volatile("cp.async.bulk.tensor.2d.shared::cluster.global.mbarrier::complete_tx::bytes.multicast::cluster [%0], [%1, {%3, %4}], [%2], %5;"
               :: "r"(dst), "l"(tm), "r"(bar), "r"(c0), "r"(c1), "h"((uint16_t)3) : "memory");
}
__device__ __forceinline__ void tma_store_2d(const CUtensorMap* tm, uint32_t src, int c0, int c1) {
  asm volatile("cp.async.bulk.tensor.2d.global.shared::cta.bulk_group [%0, {%2, %3}], [%1];"
               :: "l"(tm), "r"(src), "r"(c0), "r"(c1) : "memory");
}
__device__ __forceinline__ void bulk_commit_wait() {
  asm volatile("cp.async.bulk.commit_group;\ncp.async.bulk.wait_group 0;" ::: "memory");
}
__device__ __forceinline__ void prefetch_tmap(const CUtensorMap* tm) {
  asm volatile("prefetch.tensormap [%0];" :: "l"(tm) : "memory");
}
__device__ __forceinline__ void fence_proxy_async_global() { asm volatile("fence.proxy.async.global;" ::: "memory"); }
__device__ __forceinline__ void fence_proxy_async_smem() { asm volatile("fence.proxy.async.shared::cta;" ::: "memory"); }
__device__ __forceinline__ unsigned ld_relaxed(const unsigned* p) {
  unsigned v;
  asm volatile("ld.relaxed.gpu.global.u32 %0, [%1];" : "=r"(v) : "l"(p) : "memory");
  return v;
}
__device__ __forceinline__ void fence_acquire() { asm volatile("fence.acquire.gpu;" ::: "memory"); }
__device__ __forceinline__ void wait_flag(const unsigned* p, unsigned target) {
  int it = 0;
  while ((int)(ld_relaxed(p) - target) < 0 && ++it < (1 << 20)) {}
  fence_acquire();
}
__device__ __forceinline__ void signal_release(unsigned* p) {
  asm volatile("red.release.gpu.global.add.u32 [%0], 1;" :: "l"(p) : "memory");
}
template <int ID, int N> __device__ __forceinline__ void bar_arrive() { asm volatile("bar.arrive %0, %1;" :: "n"(ID), "n"(N) : "memory"); }
template <int ID, int N> __device__ __forceinline__ void bar_sync() { asm volatile("bar.sync %0, %1;" :: "n"(ID), "n"(N) : "memory"); }
__device__ __forceinline__ void bar_wg(int wg) { asm volatile("bar.sync %0, 128;" :: "r"(2 + wg) : "memory"); }
__device__ __forceinline__ void cluster_sync() {
  asm volatile("barrier.cluster.arrive.relaxed.aligned;\nbarrier.cluster.wait.aligned;" ::: "memory");
}
__device__ __forceinline__ void cluster_wait() { asm volatile("barrier.cluster.wait.acquire.aligned;" ::: "memory"); }
enum { BAR_X1 = 7, BAR_WF = 8  , BAR_SKEW = 10 };

__device__ __forceinline__ void wgmma_fence() { asm volatile("wgmma.fence.sync.aligned;" ::: "memory"); }
__device__ __forceinline__ void wgmma_commit() { asm volatile("wgmma.commit_group.sync.aligned;" ::: "memory"); }
template <int N> __device__ __forceinline__ void wgmma_wait() { asm volatile("wgmma.wait_group.sync.aligned %0;" :: "n"(N) : "memory"); }

template <int scale_d, int tnsp_b = 1> __device__ __forceinline__ void wgmma_n192(float* d, uint64_t descA, uint64_t descB) {
  asm volatile("{\n.reg .pred p;\nsetp.ne.b32 p, %98, 0;\n"
               "wgmma.mma_async.sync.aligned.m64n192k16.f32.bf16.bf16 {%0,%1,%2,%3,%4,%5,%6,%7,%8,%9,%10,%11,%12,%13,%14,%15,%16,%17,%18,%19,%20,%21,%22,%23,%24,%25,%26,%27,%28,%29,%30,%31,%32,%33,%34,%35,%36,%37,%38,%39,%40,%41,%42,%43,%44,%45,%46,%47,%48,%49,%50,%51,%52,%53,%54,%55,%56,%57,%58,%59,%60,%61,%62,%63,%64,%65,%66,%67,%68,%69,%70,%71,%72,%73,%74,%75,%76,%77,%78,%79,%80,%81,%82,%83,%84,%85,%86,%87,%88,%89,%90,%91,%92,%93,%94,%95}, %96, %97, p, 1, 1, 0, %99;\n}\n"
               : "+f"(d[0]), "+f"(d[1]), "+f"(d[2]), "+f"(d[3]), "+f"(d[4]), "+f"(d[5]), "+f"(d[6]), "+f"(d[7]), "+f"(d[8]), "+f"(d[9]), "+f"(d[10]), "+f"(d[11]), "+f"(d[12]), "+f"(d[13]), "+f"(d[14]), "+f"(d[15]), "+f"(d[16]), "+f"(d[17]), "+f"(d[18]), "+f"(d[19]), "+f"(d[20]), "+f"(d[21]), "+f"(d[22]), "+f"(d[23]), "+f"(d[24]), "+f"(d[25]), "+f"(d[26]), "+f"(d[27]), "+f"(d[28]), "+f"(d[29]), "+f"(d[30]), "+f"(d[31]), "+f"(d[32]), "+f"(d[33]), "+f"(d[34]), "+f"(d[35]), "+f"(d[36]), "+f"(d[37]), "+f"(d[38]), "+f"(d[39]), "+f"(d[40]), "+f"(d[41]), "+f"(d[42]), "+f"(d[43]), "+f"(d[44]), "+f"(d[45]), "+f"(d[46]), "+f"(d[47]), "+f"(d[48]), "+f"(d[49]), "+f"(d[50]), "+f"(d[51]), "+f"(d[52]), "+f"(d[53]), "+f"(d[54]), "+f"(d[55]), "+f"(d[56]), "+f"(d[57]), "+f"(d[58]), "+f"(d[59]), "+f"(d[60]), "+f"(d[61]), "+f"(d[62]), "+f"(d[63]), "+f"(d[64]), "+f"(d[65]), "+f"(d[66]), "+f"(d[67]), "+f"(d[68]), "+f"(d[69]), "+f"(d[70]), "+f"(d[71]), "+f"(d[72]), "+f"(d[73]), "+f"(d[74]), "+f"(d[75]), "+f"(d[76]), "+f"(d[77]), "+f"(d[78]), "+f"(d[79]), "+f"(d[80]), "+f"(d[81]), "+f"(d[82]), "+f"(d[83]), "+f"(d[84]), "+f"(d[85]), "+f"(d[86]), "+f"(d[87]), "+f"(d[88]), "+f"(d[89]), "+f"(d[90]), "+f"(d[91]), "+f"(d[92]), "+f"(d[93]), "+f"(d[94]), "+f"(d[95])
               : "l"(descA), "l"(descB), "n"(scale_d), "n"(tnsp_b));
}
template <int scale_d> __device__ __forceinline__ void wgmma4_n192(float* d, uint32_t da, uint32_t db) {
#define R_ "{%0,%1,%2,%3,%4,%5,%6,%7,%8,%9,%10,%11,%12,%13,%14,%15,%16,%17,%18,%19,%20,%21,%22,%23,%24,%25,%26,%27,%28,%29,%30,%31,%32,%33,%34,%35,%36,%37,%38,%39,%40,%41,%42,%43,%44,%45,%46,%47,%48,%49,%50,%51,%52,%53,%54,%55,%56,%57,%58,%59,%60,%61,%62,%63,%64,%65,%66,%67,%68,%69,%70,%71,%72,%73,%74,%75,%76,%77,%78,%79,%80,%81,%82,%83,%84,%85,%86,%87,%88,%89,%90,%91,%92,%93,%94,%95}"
  asm volatile("{\n.reg .pred p, q;\n.reg .b64 a, b;\nsetp.ne.b32 p, %98, 0;\nsetp.eq.b32 q, 0, 0;\nmov.b64 a, {%96, 0x40000040};\nmov.b64 b, {%97, 0x40000040};\n"
               "wgmma.mma_async.sync.aligned.m64n192k16.f32.bf16.bf16 " R_ ", a, b, p, 1, 1, 0, 1;\nadd.s64 a, a, 2;\nadd.s64 b, b, 128;\n"
               "wgmma.mma_async.sync.aligned.m64n192k16.f32.bf16.bf16 " R_ ", a, b, q, 1, 1, 0, 1;\nadd.s64 a, a, 2;\nadd.s64 b, b, 128;\n"
               "wgmma.mma_async.sync.aligned.m64n192k16.f32.bf16.bf16 " R_ ", a, b, q, 1, 1, 0, 1;\nadd.s64 a, a, 2;\nadd.s64 b, b, 128;\n"
               "wgmma.mma_async.sync.aligned.m64n192k16.f32.bf16.bf16 " R_ ", a, b, q, 1, 1, 0, 1;\n}\n"
               : "+f"(d[0]), "+f"(d[1]), "+f"(d[2]), "+f"(d[3]), "+f"(d[4]), "+f"(d[5]), "+f"(d[6]), "+f"(d[7]), "+f"(d[8]), "+f"(d[9]), "+f"(d[10]), "+f"(d[11]), "+f"(d[12]), "+f"(d[13]), "+f"(d[14]), "+f"(d[15]), "+f"(d[16]), "+f"(d[17]), "+f"(d[18]), "+f"(d[19]), "+f"(d[20]), "+f"(d[21]), "+f"(d[22]), "+f"(d[23]), "+f"(d[24]), "+f"(d[25]), "+f"(d[26]), "+f"(d[27]), "+f"(d[28]), "+f"(d[29]), "+f"(d[30]), "+f"(d[31]), "+f"(d[32]), "+f"(d[33]), "+f"(d[34]), "+f"(d[35]), "+f"(d[36]), "+f"(d[37]), "+f"(d[38]), "+f"(d[39]), "+f"(d[40]), "+f"(d[41]), "+f"(d[42]), "+f"(d[43]), "+f"(d[44]), "+f"(d[45]), "+f"(d[46]), "+f"(d[47]), "+f"(d[48]), "+f"(d[49]), "+f"(d[50]), "+f"(d[51]), "+f"(d[52]), "+f"(d[53]), "+f"(d[54]), "+f"(d[55]), "+f"(d[56]), "+f"(d[57]), "+f"(d[58]), "+f"(d[59]), "+f"(d[60]), "+f"(d[61]), "+f"(d[62]), "+f"(d[63]), "+f"(d[64]), "+f"(d[65]), "+f"(d[66]), "+f"(d[67]), "+f"(d[68]), "+f"(d[69]), "+f"(d[70]), "+f"(d[71]), "+f"(d[72]), "+f"(d[73]), "+f"(d[74]), "+f"(d[75]), "+f"(d[76]), "+f"(d[77]), "+f"(d[78]), "+f"(d[79]), "+f"(d[80]), "+f"(d[81]), "+f"(d[82]), "+f"(d[83]), "+f"(d[84]), "+f"(d[85]), "+f"(d[86]), "+f"(d[87]), "+f"(d[88]), "+f"(d[89]), "+f"(d[90]), "+f"(d[91]), "+f"(d[92]), "+f"(d[93]), "+f"(d[94]), "+f"(d[95])
               : "r"(da), "r"(db), "n"(scale_d));
#undef R_
}
template <int scale_d> __device__ __forceinline__ void wgmma4_n128(float* d, uint32_t da, uint32_t db) {
#define R_ "{%0,%1,%2,%3,%4,%5,%6,%7,%8,%9,%10,%11,%12,%13,%14,%15,%16,%17,%18,%19,%20,%21,%22,%23,%24,%25,%26,%27,%28,%29,%30,%31,%32,%33,%34,%35,%36,%37,%38,%39,%40,%41,%42,%43,%44,%45,%46,%47,%48,%49,%50,%51,%52,%53,%54,%55,%56,%57,%58,%59,%60,%61,%62,%63}"
  asm volatile("{\n.reg .pred p, q;\n.reg .b64 a, b;\nsetp.ne.b32 p, %66, 0;\nsetp.eq.b32 q, 0, 0;\nmov.b64 a, {%64, 0x40000040};\nmov.b64 b, {%65, 0x40000040};\n"
               "wgmma.mma_async.sync.aligned.m64n128k16.f32.bf16.bf16 " R_ ", a, b, p, 1, 1, 0, 1;\nadd.s64 a, a, 2;\nadd.s64 b, b, 128;\n"
               "wgmma.mma_async.sync.aligned.m64n128k16.f32.bf16.bf16 " R_ ", a, b, q, 1, 1, 0, 1;\nadd.s64 a, a, 2;\nadd.s64 b, b, 128;\n"
               "wgmma.mma_async.sync.aligned.m64n128k16.f32.bf16.bf16 " R_ ", a, b, q, 1, 1, 0, 1;\nadd.s64 a, a, 2;\nadd.s64 b, b, 128;\n"
               "wgmma.mma_async.sync.aligned.m64n128k16.f32.bf16.bf16 " R_ ", a, b, q, 1, 1, 0, 1;\n}\n"
               : "+f"(d[0]), "+f"(d[1]), "+f"(d[2]), "+f"(d[3]), "+f"(d[4]), "+f"(d[5]), "+f"(d[6]), "+f"(d[7]), "+f"(d[8]), "+f"(d[9]), "+f"(d[10]), "+f"(d[11]), "+f"(d[12]), "+f"(d[13]), "+f"(d[14]), "+f"(d[15]), "+f"(d[16]), "+f"(d[17]), "+f"(d[18]), "+f"(d[19]), "+f"(d[20]), "+f"(d[21]), "+f"(d[22]), "+f"(d[23]), "+f"(d[24]), "+f"(d[25]), "+f"(d[26]), "+f"(d[27]), "+f"(d[28]), "+f"(d[29]), "+f"(d[30]), "+f"(d[31]), "+f"(d[32]), "+f"(d[33]), "+f"(d[34]), "+f"(d[35]), "+f"(d[36]), "+f"(d[37]), "+f"(d[38]), "+f"(d[39]), "+f"(d[40]), "+f"(d[41]), "+f"(d[42]), "+f"(d[43]), "+f"(d[44]), "+f"(d[45]), "+f"(d[46]), "+f"(d[47]), "+f"(d[48]), "+f"(d[49]), "+f"(d[50]), "+f"(d[51]), "+f"(d[52]), "+f"(d[53]), "+f"(d[54]), "+f"(d[55]), "+f"(d[56]), "+f"(d[57]), "+f"(d[58]), "+f"(d[59]), "+f"(d[60]), "+f"(d[61]), "+f"(d[62]), "+f"(d[63])
               : "r"(da), "r"(db), "n"(scale_d));
#undef R_
}
template <int scale_d> __device__ __forceinline__ void wgmma_n32(float* d, uint64_t descA, uint64_t descB) {
  asm volatile("{\n.reg .pred p;\nsetp.ne.b32 p, %18, 0;\n"
               "wgmma.mma_async.sync.aligned.m64n32k16.f32.bf16.bf16 {%0,%1,%2,%3,%4,%5,%6,%7,%8,%9,%10,%11,%12,%13,%14,%15}, %16, %17, p, 1, 1, 0, 1;\n}\n"
               : "+f"(d[0]), "+f"(d[1]), "+f"(d[2]), "+f"(d[3]), "+f"(d[4]), "+f"(d[5]), "+f"(d[6]), "+f"(d[7]), "+f"(d[8]), "+f"(d[9]), "+f"(d[10]), "+f"(d[11]), "+f"(d[12]), "+f"(d[13]), "+f"(d[14]), "+f"(d[15])
               : "l"(descA), "l"(descB), "n"(scale_d));
}
template <int scale_d, int tnsp_a> __device__ __forceinline__ void wgmma_n40(float* d, uint64_t descA, uint64_t descB) {
  asm volatile("{\n.reg .pred p;\nsetp.ne.b32 p, %22, 0;\n"
               "wgmma.mma_async.sync.aligned.m64n40k16.f32.bf16.bf16 {%0,%1,%2,%3,%4,%5,%6,%7,%8,%9,%10,%11,%12,%13,%14,%15,%16,%17,%18,%19}, %20, %21, p, 1, 1, %23, 1;\n}\n"
               : "+f"(d[0]), "+f"(d[1]), "+f"(d[2]), "+f"(d[3]), "+f"(d[4]), "+f"(d[5]), "+f"(d[6]), "+f"(d[7]), "+f"(d[8]), "+f"(d[9]), "+f"(d[10]), "+f"(d[11]), "+f"(d[12]), "+f"(d[13]), "+f"(d[14]), "+f"(d[15]), "+f"(d[16]), "+f"(d[17]), "+f"(d[18]), "+f"(d[19])
               : "l"(descA), "l"(descB), "n"(scale_d), "n"(tnsp_a));
}
template <int scale_d> __device__ __forceinline__ void wgmma_n40_rs(float* d, const uint32_t* a, uint64_t descB) {
  asm volatile("{\n.reg .pred p;\nsetp.ne.b32 p, %25, 0;\n"
               "wgmma.mma_async.sync.aligned.m64n40k16.f32.bf16.bf16 {%0,%1,%2,%3,%4,%5,%6,%7,%8,%9,%10,%11,%12,%13,%14,%15,%16,%17,%18,%19}, {%20,%21,%22,%23}, %24, p, 1, 1, 1;\n}\n"
               : "+f"(d[0]), "+f"(d[1]), "+f"(d[2]), "+f"(d[3]), "+f"(d[4]), "+f"(d[5]), "+f"(d[6]), "+f"(d[7]), "+f"(d[8]), "+f"(d[9]), "+f"(d[10]), "+f"(d[11]), "+f"(d[12]), "+f"(d[13]), "+f"(d[14]), "+f"(d[15]), "+f"(d[16]), "+f"(d[17]), "+f"(d[18]), "+f"(d[19])
               : "r"(a[0]), "r"(a[1]), "r"(a[2]), "r"(a[3]), "l"(descB), "n"(scale_d));
}
__device__ __forceinline__ uint64_t make_desc(uint32_t addr, uint32_t lbo_bytes, uint32_t sbo_bytes) {
  return (uint64_t)((addr & 0x3FFFF) >> 4) | ((uint64_t)(lbo_bytes >> 4) << 16) | ((uint64_t)(sbo_bytes >> 4) << 32) | (1ull << 62);
}

__device__ __forceinline__ void ldsm_x4(uint32_t addr, uint32_t& r0, uint32_t& r1, uint32_t& r2, uint32_t& r3) {
  asm volatile("ldmatrix.sync.aligned.m8n8.x4.shared.b16 {%0,%1,%2,%3}, [%4];" : "=r"(r0), "=r"(r1), "=r"(r2), "=r"(r3) : "r"(addr) : "memory");
}
__device__ __forceinline__ void ldsm_x4_t(uint32_t addr, uint32_t& r0, uint32_t& r1, uint32_t& r2, uint32_t& r3) {
  asm volatile("ldmatrix.sync.aligned.m8n8.x4.trans.shared.b16 {%0,%1,%2,%3}, [%4];" : "=r"(r0), "=r"(r1), "=r"(r2), "=r"(r3) : "r"(addr) : "memory");
}
__device__ __forceinline__ void stsm_x4(uint32_t addr, uint32_t r0, uint32_t r1, uint32_t r2, uint32_t r3) {
  asm volatile("stmatrix.sync.aligned.m8n8.x4.shared.b16 [%0], {%1,%2,%3,%4};" :: "r"(addr), "r"(r0), "r"(r1), "r"(r2), "r"(r3) : "memory");
}
__device__ __forceinline__ void sts128(uint32_t addr, uint32_t a, uint32_t b, uint32_t c, uint32_t d) {
  asm volatile("st.shared.v4.u32 [%0], {%1,%2,%3,%4};" :: "r"(addr), "r"(a), "r"(b), "r"(c), "r"(d) : "memory");
}
__device__ __forceinline__ float lds32f(uint32_t addr) {
  float v;
  asm volatile("ld.shared.f32 %0, [%1];" : "=f"(v) : "r"(addr) : "memory");
  return v;
}
__device__ __forceinline__ void sts32f(uint32_t addr, float a) {
  asm volatile("st.shared.f32 [%0], %1;" :: "r"(addr), "f"(a) : "memory");
}
__device__ __forceinline__ void mma_bf16(float (&c)[4], uint32_t a0, uint32_t a1, uint32_t a2, uint32_t a3, uint32_t b0, uint32_t b1) {
  asm volatile("mma.sync.aligned.m16n8k16.row.col.f32.bf16.bf16.f32 {%0,%1,%2,%3}, {%4,%5,%6,%7}, {%8,%9}, {%0,%1,%2,%3};"
               : "+f"(c[0]), "+f"(c[1]), "+f"(c[2]), "+f"(c[3]) : "r"(a0), "r"(a1), "r"(a2), "r"(a3), "r"(b0), "r"(b1));
}
__device__ __forceinline__ void mma_bf16_z(float (&c)[4], uint32_t a0, uint32_t a1, uint32_t a2, uint32_t a3, uint32_t b0, uint32_t b1) {
  asm volatile("mma.sync.aligned.m16n8k16.row.col.f32.bf16.bf16.f32 {%0,%1,%2,%3}, {%4,%5,%6,%7}, {%8,%9}, {%10,%10,%10,%10};"
               : "=f"(c[0]), "=f"(c[1]), "=f"(c[2]), "=f"(c[3]) : "r"(a0), "r"(a1), "r"(a2), "r"(a3), "r"(b0), "r"(b1), "f"(0.f));
}
__device__ __forceinline__ uint32_t movm_t(uint32_t v) {
  uint32_t r;
  asm volatile("movmatrix.sync.aligned.m8n8.trans.b16 %0, %1;" : "=r"(r) : "r"(v));
  return r;
}
__device__ __forceinline__ uint32_t pack_bf16(float lo, float hi) {
  uint32_t r;
  asm("cvt.rn.bf16x2.f32 %0, %1, %2;" : "=r"(r) : "f"(hi), "f"(lo));
  return r;
}
__device__ __forceinline__ float bf_lo(uint32_t v) { return __uint_as_float(v << 16); }
__device__ __forceinline__ float bf_hi(uint32_t v) { return __uint_as_float(v & 0xFFFF0000u); }
__device__ __forceinline__ void split3(float x, uint32_t& h, uint32_t& m, uint32_t& l) {
  h = pack_bf16(x, 0.f); x -= bf_lo(h);
  m = pack_bf16(x, 0.f); x -= bf_lo(m);
  l = pack_bf16(x, 0.f);
}
__device__ __forceinline__ float ex2(float x) { float r; asm("ex2.approx.ftz.f32 %0, %1;" : "=f"(r) : "f"(x)); return r; }
__device__ __forceinline__ float rcp_fast(float x) { float r; asm("rcp.approx.ftz.f32 %0, %1;" : "=f"(r) : "f"(x)); return r; }
__device__ __forceinline__ void red_v4(float* p, float a, float b, float c, float d) {
  asm volatile("red.global.add.v4.f32 [%0], {%1, %2, %3, %4};" :: "l"(p), "f"(a), "f"(b), "f"(c), "f"(d) : "memory");
}
__device__ __forceinline__ uint4 ld_ll(const uint4* p) {
  uint4 v;
  asm volatile("{\n.reg .b64 a, b;\nld.relaxed.gpu.global.v2.b64 {a, b}, [%4];\nmov.b64 {%0, %1}, a;\nmov.b64 {%2, %3}, b;\n}\n"
               : "=r"(v.x), "=r"(v.y), "=r"(v.z), "=r"(v.w) : "l"(p) : "memory");
  return v;
}
__device__ __forceinline__ void st_b64(uint2* p, uint32_t a, uint32_t b) {
  asm volatile("{\n.reg .b64 v;\nmov.b64 v, {%1, %2};\nst.relaxed.gpu.global.b64 [%0], v;\n}\n" :: "l"(p), "r"(a), "r"(b) : "memory");
}
__device__ __forceinline__ void st_b128(uint4* p, uint32_t a, uint32_t b, uint32_t c, uint32_t d) {
  asm volatile("{\n.reg .b128 v;\nmov.b128 v, {%1, %2, %3, %4};\nst.relaxed.gpu.global.b128 [%0], v;\n}\n" :: "l"(p), "r"(a), "r"(b), "r"(c), "r"(d) : "memory");
}
__device__ __forceinline__ uint4 ld_b128(const uint4* p) {
  uint4 v;
  asm volatile("{\n.reg .b128 v;\nld.relaxed.gpu.global.b128 v, [%4];\nmov.b128 {%0, %1, %2, %3}, v;\n}\n" : "=r"(v.x), "=r"(v.y), "=r"(v.z), "=r"(v.w) : "l"(p) : "memory");
  return v;
}

constexpr float LOG2E = 1.4426950408889634f;

struct Params {
  const __nv_bfloat16* x0;
  const __nv_bfloat16* wA_qkv;
  const __nv_bfloat16* wA_o;
  const __nv_bfloat16* wB_qkv;
  const __nv_bfloat16* wB_phi;
  const __nv_bfloat16* wB_o;
  __nv_bfloat16* out;
};

#define ACC_DEF(d, n) _Pragma("unroll") for (int i_ = 0; i_ < (n); i_++) asm volatile("" : "=f"(d[i_]))
#define ACC_FENCE(d, n) _Pragma("unroll") for (int i_ = 0; i_ < (n); i_++) asm volatile("" : "+f"(d[i_]) :: "memory")
#define PIN(a, n) _Pragma("unroll") for (int i_ = 0; i_ < (n); i_++) asm volatile("" : "+f"((a)[i_]))
#define PINU(a, n) _Pragma("unroll") for (int i_ = 0; i_ < (n); i_++) asm volatile("" : "+r"((a)[i_]))

#define V_ADDR(p0) uint32_t va_[2] = {(p0) + (srowoff >> 1) + (lhi ^ lsw2), (p0) + (srowoff >> 1) + ((32 + lhi) ^ lsw2)}
#define STAGE_V(acc) { \
    _Pragma("unroll") for (int j_ = 0; j_ < 4; j_++) { \
      const float* a_ = (acc) + j_ * 8; \
      stsm_x4(va_[j_ & 1] + (j_ >> 1) * 8192, \
              pack_bf16(rs0 * a_[0], rs0 * a_[1]), pack_bf16(rs1 * a_[2], rs1 * a_[3]), pack_bf16(rs0 * a_[4], rs0 * a_[5]), pack_bf16(rs1 * a_[6], rs1 * a_[7])); } }
#define FRAG(dst, acc, TR, grp) { \
    _Pragma("unroll") for (int i_ = 0; i_ < 16; i_++) { \
      const float r_ = (i_ & 1) ? rs1 : rs0; \
      const uint32_t w_ = pack_bf16(r_ * (acc)[2 * i_], r_ * (acc)[2 * i_ + 1]); \
      if (TR) (dst)[i_] = movm_t(w_); else (dst)[(i_ & 12) + (i_ & 1) * 2 + ((i_ >> 1) & 1)] = w_; } \
    if (warp == 7 && mm < 15) { \
      _Pragma("unroll") for (int j_ = 0; j_ < 4; j_++) \
        st_b128(g_halo + (size_t)(mm * 8 + jj) * 512 + ((grp) * 4 + j_) * 32 + lane, ((dst)[j_ * 4] & ~1u) | H_BIT(l), (dst)[j_ * 4 + 1], (dst)[j_ * 4 + 2], (dst)[j_ * 4 + 3]); } \
    PINU(dst, 16); }
#define FRAG_PUT(src, slot) if (warp < 7) { _Pragma("unroll") for (int j_ = 0; j_ < 4; j_++) \
      sts128(sbase + (slot) * SLOT + 2048 + warp * 2048 + j_ * 512 + lane * 16, (src)[j_ * 4], (src)[j_ * 4 + 1], (src)[j_ * 4 + 2], (src)[j_ * 4 + 3]); }
#define FRAG_GET(dst, slot) { _Pragma("unroll") for (int j_ = 0; j_ < 4; j_++) \
      asm volatile("ld.shared.v4.u32 {%0, %1, %2, %3}, [%4];" : "=r"((dst)[j_ * 4]), "=r"((dst)[j_ * 4 + 1]), "=r"((dst)[j_ * 4 + 2]), "=r"((dst)[j_ * 4 + 3]) \
                   : "r"(sbase + (slot) * SLOT + warp * 2048 + j_ * 512 + lane * 16) : "memory"); }
#define RW(j) (((j) >> 1) * 4 + ((j) & 1))
template <int POS> __device__ __forceinline__ float exps16_(float* o, const float* p) {
  float s[4];
#pragma unroll
  for (int j = 0; j < 16; j++) { o[j] = ex2(POS ? p[RW(j)] : -p[RW(j)]); if (j < 4) s[j] = o[j]; else s[j & 3] += o[j]; }
  const float r = (s[0] + s[1]) + (s[2] + s[3]);
  return r + __shfl_xor_sync(0xffffffffu, r, 1);
}
template <int POS> __device__ __forceinline__ void exps16_fix(float* o, const float* p, float& sum) {
  if (__builtin_expect(__any_sync(0xffffffffu, !(sum > SUMLO && sum < SUMHI)), 0)) {
    float m = p[0], q[32];
#pragma unroll
    for (int j = 1; j < 16; j++) m = POS ? fmaxf(m, p[RW(j)]) : fminf(m, p[RW(j)]);
    const float x = __shfl_xor_sync(0xffffffffu, m, 1);
    m = POS ? fmaxf(m, x) : fminf(m, x);
#pragma unroll
    for (int j = 0; j < 16; j++) q[RW(j)] = p[RW(j)] - m;
    sum = exps16_<POS>(o, q);
  }
}
__device__ __forceinline__ void store16(const float* e, float sum, uint32_t dst, uint32_t dsw, int c0) {
  const float inv = rcp_fast(sum);
#pragma unroll
  for (int j = 0; j < 2; j++)
    sts128(dst + (((c0 + j) << 4) ^ dsw), pack_bf16(e[j * 8] * inv, e[j * 8 + 1] * inv), pack_bf16(e[j * 8 + 2] * inv, e[j * 8 + 3] * inv),
           pack_bf16(e[j * 8 + 4] * inv, e[j * 8 + 5] * inv), pack_bf16(e[j * 8 + 6] * inv, e[j * 8 + 7] * inv));
}
template <int POS> __device__ __forceinline__ void expp16(uint32_t* o, float* p) {
  {
#pragma unroll
    for (int r = 0; r < 4; r += 2) {
      float m = p[r];
#pragma unroll
      for (int j = 1; j < 8; j++) m = POS ? fmaxf(m, p[r + RW(j)]) : fminf(m, p[r + RW(j)]);
#pragma unroll
      for (int s = 1; s <= 2; s <<= 1) { const float x = __shfl_xor_sync(0xffffffffu, m, s); m = POS ? fmaxf(m, x) : fminf(m, x); }
#pragma unroll
      for (int j = 0; j < 8; j++) p[r + RW(j)] -= m;
    }
  }
#pragma unroll
  for (int j = 0; j < 8; j++) o[j] = pack_bf16(ex2(POS ? p[2 * j] : -p[2 * j]), ex2(POS ? p[2 * j + 1] : -p[2 * j + 1]));
}
__device__ __forceinline__ void scale32(float* o, const float* p, float c0, float c1) {
#pragma unroll
  for (int i = 0; i < 32; i++) asm volatile("mul.f32 %0, %1, %2;" : "=f"(o[i]) : "f"(p[i]), "f"((i & 2) ? c1 : c0));
}
__device__ __forceinline__ bool any_big(const float* p) {
  float m[4];
#pragma unroll
  for (int i = 0; i < 32; i++) m[i >> 3] = (i & 7) ? fmaf(p[i], p[i], m[i >> 3]) : p[i] * p[i];
  return __any_sync(0xffffffffu, !(fmaxf(fmaxf(m[0], m[1]), fmaxf(m[2], m[3])) < BIGLIM));
}
__device__ __forceinline__ void phiq_a(float* p, bool big) {
  if (__builtin_expect(!big, 1)) {
#pragma unroll
    for (int j = 0; j < 16; j++) p[j] = ex2(p[j]);
  }
}
template <int NEXT> __device__ __forceinline__ void phiq_b(uint32_t* o, float* p, bool big) {
  if (__builtin_expect(big, 0)) {
    expp16<0>(o, p); expp16<1>(o + 8, p);
  } else {
    if (NEXT) phiq_a(p + 16, false);
#pragma unroll
    for (int j = 0; j < 4; j++) {
      const float a = p[4 * j], b = p[4 * j + 1], c = p[4 * j + 2], d = p[4 * j + 3];
      const float ab = a * b, cd = c * d, r = rcp_fast(ab * cd), x = r * cd, y = r * ab;
      o[2 * j] = pack_bf16(x * b, x * a); o[2 * j + 1] = pack_bf16(y * d, y * c);
      o[8 + 2 * j] = pack_bf16(a, b); o[9 + 2 * j] = pack_bf16(c, d);
    }
  }
}
#define SCHED_FENCE() asm volatile("pmevent 0;" ::: "memory")

__global__ void __cluster_dims__(2, 1, 1) __launch_bounds__(384, 1)
mega_kernel(const __grid_constant__ CUtensorMap tm_x0, const __grid_constant__ CUtensorMap tm_xo, const __grid_constant__ CUtensorMap tm_os,
            const __grid_constant__ CUtensorMap tm_o, const __grid_constant__ CUtensorMap tm_wf,
            const __grid_constant__ CUtensorMap tm_wqA, const __grid_constant__ CUtensorMap tm_wqB,
            const __grid_constant__ CUtensorMap tm_woA, const __grid_constant__ CUtensorMap tm_woB,
            const __grid_constant__ CUtensorMap tm_phi, const Params prm) {
  extern __shared__ __align__(1024) uint8_t smem_raw[];
  const uint32_t sbase = smem_u32(smem_raw);
  const uint32_t bar_full = sbase + OFF_BAR;
  const uint32_t bar_done = bar_full + 384;
  const uint32_t bar_stat = bar_full + 768, bar_stat2 = bar_full + 776, bar_epi = bar_full + 784, bar_phi = bar_full + 936  , bar_halo = bar_full + 904  ;
  const uint32_t bar_xr = bar_full + 800, bar_lx = bar_full + 808, bar_stg = bar_full + 832;
  const uint32_t bar_chk = bar_full + 848;

  const int warp = __shfl_sync(0xffffffffu, threadIdx.x >> 5, 0), lane = threadIdx.x & 31;
  uint32_t rank;
  asm volatile("mov.u32 %0, %%cluster_ctarank;" : "=r"(rank));
  const int aux = (int)blockIdx.x - NMAIN, tp = (int)(blockIdx.x >> 1) - 4;
  const int gp = tp < 0 ? 0 : (tp < 32 ? tp & 7 : 1 + (tp - 32) % 7), me = tp < 0 ? tp + 8 : (tp < 32 ? tp >> 3 : 4 + (tp - 32) / 7);
  const int jj = me, cc = gp;
  const int cta = aux >= 0 ? -1 : (cc * 8 + jj) * 2 + (int)rank;
  const int mm = cc * 2 + (int)rank;

#define LOAD_EPOCH() const unsigned epoch = ld_relaxed(&g_flags.epoch.v), ep1 = epoch + 1; (void)epoch
  int budget = 1 << 22;

  if (cta >= 0) {
    if (warp >= 8 && warp < 8 + EARLY && elect_one()) {
      const int u = warp - 8;
      const uint32_t fb = bar_full + u * 8;
      mbar_init(fb, 1);
      asm volatile("fence.mbarrier_init.release.cluster;" ::: "memory");
      fence_proxy_async_smem();
      mbar_expect_tx(fb, u < 2 ? QST + SLOT : QST);
      if (u && STAG2) __nanosleep(STAG2);
      if (u < 2) tma_load_2d(sbase + OFF_S + u * SLOT, &tm_x0, fb, jj * 128 + u * 64, mm * 128);
#pragma unroll
      for (int i = 0; i < 6; i++) tma_load_2d(sbase + u * QST + i * 4096, &tm_wqA, fb, jj * 128 + (u >> 1) * 64 + (i >> 1) * 1024, jj * 128 + (u & 1) * 64 + (i & 1) * 32);
      if (u == 0) PROFT(472);
    }
    __syncwarp();
    {
      const int tx = threadIdx.x;
      const __nv_bfloat16* pf = (tx < 128) ? prm.x0 + (size_t)(mm * 128 + tx) * D_MODEL + jj * 128
                                           : prm.wA_qkv + (size_t)(jj * 128 + (tx & 63)) * 3072 + ((tx - 128) >> 6) * 1024 + jj * 128 + rank * 64;
      if (tx < 320) { if (PF0) asm volatile("prefetch.global.L2 [%0];" :: "l"(pf)); }
      else if (tx == 320) prefetch_tmap(&tm_x0);
      else if (tx == 352) prefetch_tmap(&tm_wqA);
      else if (tx == 383) asm volatile("prefetch.global.L2 [%0];" :: "l"(&g_flags.epoch.v));
    }
    if (elect_one()) {
#pragma unroll
      for (int i = 0; i < 4; i++) {
        const int u = warp * 4 + i;
        if (u >= EARLY) mbar_init(bar_full + u * 8, ((u >= 4 && u < 11) || (u > 32 && u != 40)) ? 2 : 1); mbar_init(bar_done + u * 8, 16);
      }
      mbar_init(bar_stat + warp * 16, 0x111111181182ull >> (4 * warp) & 15);
      mbar_init(bar_stat + warp * 16 + 8, 0x111111121811ull >> (4 * warp) & 15);
      mbar_init(bar_chk + 112 + (warp & 7) * 8, 1);
      asm volatile("fence.mbarrier_init.release.cluster;" ::: "memory");
    }
    __syncthreads();
    asm volatile("barrier.cluster.arrive.relaxed.aligned;" ::: "memory");
  }

  if (cta < 0) {
    LOAD_EPOCH();
    const uint32_t buf = sbase + warp * SLOT, bar = sbase + OFF_BAR + warp * 16;
    const uint32_t lsw = (lane & 7) << 4, lhi = (lane >> 4) << 4, lrow = (lane & 15) * 128;
    const bool el = elect_one();
    if (el) {
      mbar_init(bar, 1); mbar_init(bar + 8, 1);
      asm volatile("fence.mbarrier_init.release.cluster;" ::: "memory");
    }
#pragma unroll 1
    for (int rd = 0; rd < (NLAYERS > 1 ? 5 : 2); rd++) {
      if (rd >= 2 && warp >= 8) break;
      const int tk = rd < 2 ? aux * 12 + warp : aux * 8 + warp;
      const int half = tk & 1;
      const int blk = rd < 2 ? (tk >> 1) * 2 + rd : (4 - rd) * 16 + (tk >> 1);
      const CUtensorMap* tm = rd < 2 ? &tm_wqA : (rd == 2 ? &tm_wqB : &tm_wf);
      const int j0 = (blk & 15) >> 1;
#define AUX_LOAD(n) { const uint32_t d_ = buf + ((n) & 1) * 8192, b_ = bar + ((n) & 1) * 8; const int r_ = kslice(j0, 2 * (n) + half) * 64; \
        mbar_expect_tx(b_, 8192); tma_load_2d(d_, tm, b_, blk * 64, r_); tma_load_2d(d_ + 4096, tm, b_, blk * 64, r_ + 32); }
      if (el) {
        if (rd == 3) { wait_flag(&g_flags.wfready[j0].v, ep1 * 16); fence_proxy_async_global(); }
        AUX_LOAD(0); AUX_LOAD(1);
      }
      __syncwarp();
      float cs[8][4];
#pragma unroll
      for (int i = 0; i < 8; i++) cs[i][0] = cs[i][1] = cs[i][2] = cs[i][3] = 0.f;
#pragma unroll 1
      for (int n = 0; n < 8; n++) {
        const uint32_t tb = buf + (n & 1) * 8192 + lrow;
        mbar_wait(bar + (n & 1) * 8, (n >> 1) & 1);
#pragma unroll
        for (int i = 0; i < 16; i++) {
          uint32_t b0, b1, b2, b3;
          ldsm_x4_t(tb + (i >> 2) * 2048 + (((i & 3) * 32 + lhi) ^ lsw), b0, b1, b2, b3);
          mma_bf16(cs[2 * (i & 3)], 0x3F803F80u, 0x3F803F80u, 0x3F803F80u, 0x3F803F80u, b0, b1);
          mma_bf16(cs[2 * (i & 3) + 1], 0x3F803F80u, 0x3F803F80u, 0x3F803F80u, 0x3F803F80u, b2, b3);
        }
        __syncwarp();
        if (el && n < 6) AUX_LOAD(n + 2);
        __syncwarp();
      }
      if (lane < 4) {
#pragma unroll
        for (int i = 0; i < 8; i++) st_b64(&g_colsum[rd >= 2][blk * 32 + i * 4 + lane][half], __float_as_uint(cs[i][0]), (__float_as_uint(cs[i][1]) & ~3u) | (ep1 & 3));
      }
      __syncwarp();
    }
  } else if (warp >= 8) {
    asm volatile("setmaxnreg.dec.sync.aligned.u32 40;");
    if (warp == 8) {
      const bool el = elect_one();
      cluster_wait();
      if (el) {
#pragma unroll 1
        for (int l = 0; l < NLAYERS; l++) {
          const uint32_t par = l & 1;
          const CUtensorMap* tqk = par ? &tm_wf : &tm_wqA;
          const CUtensorMap* tv = par ? &tm_wqB : &tm_wqA;
          const CUtensorMap* two = par ? &tm_woB : &tm_woA;
          if (l == 1) { LOAD_EPOCH(); wait_flag(&g_flags.wfready[jj].v, ep1 * 16); fence_proxy_async_global(); }
#pragma unroll 1
          for (int u = l ? 0 : EARLY; u < 32; u++) {
            if (u >= 4) mbar_wait_sl(bar_done + (u - 4) * 8, par);
            else if (l) mbar_wait_sl(bar_done + (43 + u + (u >> 1)) * 8, par ^ 1);
            else if (u == 1) __nanosleep(STAG1);
            else if (u == 2 && !W23) mbar_wait_sl(bar_full, 0);
            const uint32_t fb = bar_full + u * 8;
            const bool res = u < 4 ? (l || u >= 2) : (u < 11 || (u >= 18 && u < 22));
            mbar_expect_tx(fb, res ? QST : QST + SLOT);
            const int row = kslice(jj, u < 4 ? u & 1 : (u < 18 ? u - 2 : (u < 22 ? u - 6 : u - 20))) * 64 + (int)rank * 32;
            const int ps = u < 4 ? u >> 1 : (u >= 18), col = jj * 128 + ps * 64;
            const int c0 = par ? jj * 128 + (ps ? 0 : 1024) : col;
            const uint32_t dst = sbase + (u & 3) * QST + rank * 4096;
            tma_load_2d_mc(dst, tqk, fb, c0, row);
            tma_load_2d_mc(dst + 8192, tqk, fb, c0 + (par ? 64 : 1024), row);
            tma_load_2d_mc(dst + 16384, tv, fb, col + 2048, row);
            if (l == PRL && u >= PRU && u < PRU + 4) PROFT(473 + u - PRU);
          }
#pragma unroll 1
          for (int s = 0; s < 16; s++) {
            if (s < 5) { if (s != 2 && s != 4) mbar_wait_sl(bar_done + (28 + s) * 8, par); }
            else if (s != 14) mbar_wait_sl(bar_done + (27 + s - (s == 15)) * 8, par);
            const uint32_t fb = bar_full + (32 + s) * 8;
            mbar_expect_tx(fb, SLOT);
            tma_load_2d_mc(sbase + rank * 8192 + (uint32_t)((WO_BSLOT >> (4 * s)) & 15) * SLOT, two, fb, jj * 128 + (int)rank * 64, wslice(jj, s) * 64);
            const int ts = s + par;
            if (s >= 5 && ts < 8) {
              mbar_expect_tx(bar_chk - 8 + ts * 8, SLOT);
              tma_load_2d(sbase + (uint32_t)((WO_ASLOT(par) >> (4 * ts)) & 15) * SLOT, &tm_o, bar_chk - 8 + ts * 8, wslice(jj, ts) * 64, mm * 128);
            }
          }
        }
      }
      __syncwarp();
    } else if (warp == 9) {
      const bool el = elect_one();
      if (el) {
        if (!EARLY) { PROFT(472); tma_load_2d(sbase + OFF_S, &tm_x0, bar_full, jj * 128, mm * 128); }
        if (EARLY < 2) { __nanosleep(STAG1); tma_load_2d(sbase + OFF_S + SLOT, &tm_x0, bar_full + 8, jj * 128 + 64, mm * 128); }
      }
      __syncwarp();
      LOAD_EPOCH();
#pragma unroll 1
      for (int lp = 0; lp < 4 * NLAYERS; lp++) {
        const int l = lp >> 2, ph = lp & 3;
        if (ph == 3) continue;
        const uint32_t par = l & 1;
        const unsigned* pp = reinterpret_cast<const unsigned*>(g_obuf + (ph >> 1) * 64 + (size_t)(mm * 128 + (ph ? 0 : S_LEN) + (lane & 7) * 16 + (jj & 1) * 8) * D_MODEL +
                                                               (jj >> 1) * 16 + srcb(jj, lane >> 3) * 128);
        const CUtensorMap* tm = lp ? &tm_o : &tm_x0;
        const int row = mm * 128 + ((ph || !l) ? 0 : S_LEN);
        const uint32_t bit = ph ? O_BIT(l) : X_BIT(l - 1);
        const uint32_t slots = ph ? (uint32_t)(WO_ASLOT(par) >> (ph * 32 - 28)) : 0x8769876u;
        const unsigned long long fr = ph == 0 ? XPACE : ph == 1 ? (par ? 0x353535351Full : 0x35351F1Eull) : (par ? 0x27262524232232ull : 0x27262524233232ull);
        uint32_t no = (lp == 0 || (lp & 7) == 1) ? 0 : ~0u, v0 = 0, v1 = 0;
        if (lp || !AX) mbar_wait_sl(ph ? bar_done + ((uint32_t)fr & 63) * 8 : (l ? bar_done + 47 * 8 : bar_full), ph ? par : (l ? par ^ 1 : 0));
        if (el && ph) PROFT(324 + l * 16 + ph);
        __syncwarp();
        if (no) { v0 = ld_relaxed(pp); __nanosleep(POLLGAP); v1 = ld_relaxed(pp); }
#pragma unroll 1
        for (int i = 0; i < (ph == 1 ? 4 + par : 7); i++, no >>= 8) {
#pragma unroll 1
          for (int it = 0; (no & 0xFF) && it < (1 << 18); it++) {
            no &= __ballot_sync(0xffffffffu, (v0 ^ bit) & 1) >> (8 * i);
            if (no) v0 = ld_relaxed(pp);
            if (!(no & 0xFF)) break;
            no &= __ballot_sync(0xffffffffu, (v1 ^ bit) & 1) >> (8 * i);
            if (no) v1 = ld_relaxed(pp);
          }
          if (ph || i >= XP0) mbar_wait_sl(bar_done + ((uint32_t)(fr >> (8 * i)) & 63) * 8, par);
          if (el) {
            if (i == 0) PROFT(320 + l * 16 + ph);
            const uint32_t cb = bar_chk + (ph >> 1) * 112 + i * 8;
            mbar_expect_tx(cb, SLOT);
            tma_load_2d(sbase + ((slots >> (4 * i)) & 15) * SLOT, tm, cb, srcb(jj, i) * 128 + (ph >> 1) * 64, row);
          }
          __syncwarp();
        }
        if (ph == 0 && el) {
          if (l) { wait_flag(&g_flags.xready[l][mm].v, ep1 * 8); fence_proxy_async_global(); }
#pragma unroll 1
          for (int u = 11; u < 34; u++) {
            if (u == 18) u = 22;
            mbar_wait_sl(bar_done + (u - 4) * 8, par);
            if (u == 32) mbar_expect_tx(bar_xr, 2 * SLOT);
            tma_load_2d(sbase + OFF_RA + (u & 3) * SLOT, tm, u < 32 ? bar_full + u * 8 : bar_xr, kslice(jj, u < 18 ? u - 2 : (u < 32 ? u - 20 : u - 32)) * 64, row);
          }
        }
        __syncwarp();
      }
      if (el && atomicAdd(&g_flags.done.v, 1) == ep1 * NMAIN - 1) asm volatile("st.relaxed.gpu.global.u32 [%0], %1;" :: "l"(&g_flags.epoch.v), "r"(ep1) : "memory");
      __syncwarp();
      cluster_wait();
    } else {
      const int hw = warp - 10;
      LOAD_EPOCH();
      const bool el = elect_one();
      cluster_wait();
      if (hw == 0) {
        mbar_wait_sl(bar_full + 8, 0);
        if (lane < 7) prefetch_tmap(lane == 0 ? &tm_os : lane == 1 ? &tm_o : lane == 2 ? &tm_wf : lane == 3 ? &tm_wqB : lane == 4 ? &tm_woA : lane == 5 ? &tm_woB : &tm_phi);
#pragma unroll 1
        for (int i = 0; i < (NLAYERS > 1 ? 9 : 0); i++) {
          if (i == 0 || i == 5) mbar_wait_sl(bar_done + (i >> 1) * 12, 0);
          if (el) {
            if (i == 0) { mbar_expect_tx(bar_phi, 2 * SLOT + 8192); tma_load_2d(sbase + OFF_PHI, &tm_phi, bar_phi, 0, jj * 128); }
            else tma_load_2d(sbase + (i > 4 ? 10 : 12) * SLOT - 4096 + i * 4096, &tm_wqB, bar_phi, (i > 4 ? 896 : 0) + jj * 128 + ((i - 1) >> 1) * 64, mm * 64 + (~i & 1) * 32);
          }
          __syncwarp();
          __nanosleep(PFGAP);
        }
      } else {
#pragma unroll 1
        for (int b = 0; b < 2; b++) {
          float4* z = reinterpret_cast<float4*>(g_kv[b] + (jj * 4) * KVH + mm * (4 * KVH / 16)) + lane;
#pragma unroll
          for (int i = 0; i < 6; i++) z[i * 32] = make_float4(0.f, 0.f, 0.f, 0.f);
        }
#pragma unroll 1
        for (int i = 0; i < 16; i++) {
          const int b = i >> 2;
          const uint32_t v = (b == 0 ? O_BIT(0) : b == 1 ? X_BIT(0) : H_BIT(0)) + 1;
          uint4* p = b < 2 ? reinterpret_cast<uint4*>(g_obuf + (size_t)(b * S_LEN + mm * 128 + (i & 3) * 32 + (lane >> 3) * 8) * D_MODEL + jj * 128 + (b ? 0 : 64)) + (lane & 7)
                           : g_halo + (size_t)(mm * 8 + jj) * 512 + i * 32 + lane;
          *p = make_uint4(v, v, v, v);
        }
        fence_proxy_async_global();
      }
      __syncwarp();
      uint32_t chkp = 0;
#pragma unroll 1
      for (int lp = 0; lp < 4 * NLAYERS; lp++) {
        const int l = lp >> 2, ph = (lp & 3) == 2 ? 2 - hw : (lp & 3);
        const uint32_t par = l & 1;
        int lane; asm volatile("mov.u32 %0, %%laneid;" : "=r"(lane));
        if ((lp & 3) == 2 || (hw && ph == 0)) {
          const uint32_t bit = ph ? O_BIT(l) : X_BIT(l - 1);
          uint32_t slots = ph ? (uint32_t)(WO_ASLOT(par) >> (ph * 32 - 28)) : 0x8769876u;
          const uint32_t a0 = sbase + (lane & 7) * 132 + (lane >> 3) * 32;
#pragma unroll 1
          for (int c = 0; c < 7; c++, slots >>= 4) {
            const uint32_t cb = bar_chk + 112 - hw * 112 + c * 8;
#pragma unroll 1
            for (int it = 0; it < (1 << 12); it++) {
              mbar_wait_sl(cb, (chkp >> c) & 1);
              chkp ^= 1u << c;
              if (el && c == 0) PROFT(ph == 1 ? 480 + l * 2 : 488 + l * 2 + (ph >> 1));
              if (lp == 0) break;
              uint32_t bad;
              asm volatile("{\n.reg .b32 w<16>;\n"
                           "ld.shared.u32 w0, [%1 + 0];\n"
                           "ld.shared.u32 w1, [%1 + 1024];\n"
                           "ld.shared.u32 w2, [%1 + 2048];\n"
                           "ld.shared.u32 w3, [%1 + 3072];\n"
                           "ld.shared.u32 w4, [%1 + 4096];\n"
                           "ld.shared.u32 w5, [%1 + 5120];\n"
                           "ld.shared.u32 w6, [%1 + 6144];\n"
                           "ld.shared.u32 w7, [%1 + 7168];\n"
                           "ld.shared.u32 w8, [%1 + 8192];\n"
                           "ld.shared.u32 w9, [%1 + 9216];\n"
                           "ld.shared.u32 w10, [%1 + 10240];\n"
                           "ld.shared.u32 w11, [%1 + 11264];\n"
                           "ld.shared.u32 w12, [%1 + 12288];\n"
                           "ld.shared.u32 w13, [%1 + 13312];\n"
                           "ld.shared.u32 w14, [%1 + 14336];\n"
                           "ld.shared.u32 w15, [%1 + 15360];\n"
                           "lop3.b32 w0, w0, w1, %2, 0x7E;\n"
                           "lop3.b32 w2, w2, w3, %2, 0x7E;\n"
                           "lop3.b32 w4, w4, w5, %2, 0x7E;\n"
                           "lop3.b32 w6, w6, w7, %2, 0x7E;\n"
                           "lop3.b32 w8, w8, w9, %2, 0x7E;\n"
                           "lop3.b32 w10, w10, w11, %2, 0x7E;\n"
                           "lop3.b32 w12, w12, w13, %2, 0x7E;\n"
                           "lop3.b32 w14, w14, w15, %2, 0x7E;\n"
                           "lop3.b32 w0, w0, w2, w4, 0xFE;\nlop3.b32 w6, w6, w8, w10, 0xFE;\nlop3.b32 w0, w0, w12, w14, 0xFE;\nlop3.b32 %0, w0, w6, 1, 0xA8;\n}\n"
                           : "=r"(bad) : "r"(a0 + (slots & 15) * SLOT), "r"(bit) : "memory");
              if (__all_sync(0xffffffffu, bad == 0)) break;
              if (el) {
                fence_proxy_async_smem();
                mbar_expect_tx(cb, SLOT);
                tma_load_2d(sbase + (slots & 15) * SLOT, &tm_o, cb, srcb(jj, c) * 128 + (ph >> 1) * 64, mm * 128 + (ph ? 0 : S_LEN));
                RETRY_COUNT();
              }
              __syncwarp();
            }
            if (el) { mbar_arrive_local(bar_full + (c + (ph ? 25 + ph * 8 : 4)) * 8); if (lp == PRL * 4 && c == 0) PROFT(477); }
            __syncwarp();
          }
          if (ph) continue;
#pragma unroll 1
          for (int hp = 0; hp < 2; hp++) {
            const uint4* src = reinterpret_cast<const uint4*>(g_colsum[par][jj * 64 + hp * 32 + lane]);
            uint32_t bad;
            int it = 0;
            float c[6];
            do {
              bad = 0;
#pragma unroll
              for (int p = 0; p < 3; p++) {
                const uint4 v = ld_ll(src + ((par && p < 2) ? (hp ? -32 : 512) + p * 32 : p * 512));
                bad |= (v.y ^ ep1) | (v.w ^ ep1);
                c[2 * p] = __uint_as_float(v.x) + __uint_as_float(v.z); c[2 * p + 1] = __uint_as_float(v.y) + __uint_as_float(v.w);
              }
              bad &= 3;
              if (bad) __nanosleep(300);
            } while (bad && ++it < (1 << 16));
#pragma unroll
            for (int p = 0; p < 6; p++) {
              uint32_t h, m, lo;
              split3(c[p], h, m, lo);
              sts128(sbase + OFF_LNB + hp * 4096 + (p >> 1) * 1024 + lane * 32 + (p & 1) * 16, h | (m << 16), h | (lo << 16), h | (m << 16), lo | (m << 16));
            }
            fence_proxy_async_smem();
            __syncwarp();
            if (el) { mbar_arrive_local(hp ? bar_stat2 : bar_stat); if (hp == 0) PROFT(324 + l * 16); }
            __syncwarp();
          }
          continue;
        } else if (ph == 0) {
          mbar_wait_sl(bar_done + 24, par);
          const uint4* sp = reinterpret_cast<const uint4*>(g_stats + (size_t)(mm * 128) * 8) + lane;
#pragma unroll 1
          for (int hf = 0; hf < 4; hf++) {
            uint4 v[4];
            uint32_t bad;
            int it = 0;
            do {
              bad = 0;
#pragma unroll
              for (int i = 0; i < 4; i++) { v[i] = ld_ll(sp + (hf * 4 + i) * 32); bad |= (v[i].y ^ STAT_TAG(l)) | (v[i].w ^ STAT_TAG(l)); }
              bad &= 3;
              if (bad) __nanosleep(200);
            } while (bad && ++it < (1 << 16));
            __syncwarp();
            float mean = 0.f, m2 = 0.f;
#pragma unroll
            for (int i = 0; i < 4; i++) {
              float a = __uint_as_float(v[i].x) + __uint_as_float(v[i].z);
              a += __shfl_xor_sync(0xffffffffu, a, 1); a += __shfl_xor_sync(0xffffffffu, a, 2);
              a *= 0.125f;
              const float e0 = __uint_as_float(v[i].x) - a, e1 = __uint_as_float(v[i].z) - a;
              float q = fmaf(fmaf(e0, e0, e1 * e1), 128.f, __uint_as_float(v[i].y) + __uint_as_float(v[i].w));
              q += __shfl_xor_sync(0xffffffffu, q, 1); q += __shfl_xor_sync(0xffffffffu, q, 2);
              if ((lane & 3) == i) { mean = a; m2 = q; }
            }
            const uint32_t row = hf * 32 + (lane & 3) * 8 + (lane >> 2);
            uint32_t h, m, lo;
            split3(-0.5f * mean, h, m, lo);
            sts128(sbase + OFF_LNA + row * 16, h | (h << 16), m | (h << 16), lo | (m << 16), m | (lo << 16));
            sts32f(sbase + OFF_ST + row * 4, rsqrtf(m2 * (1.f / 1024.f) + 1e-5f));
          }
          fence_proxy_async_smem();
          __syncwarp();
          if (el) { mbar_arrive_local(bar_stat); PROFT(323 + l * 16); }
          __syncwarp();
#pragma unroll 1
          for (int i = 0; i < 8 - 4 * l; i++) {
            asm volatile("prefetch.global.L2 [%0];" :: "l"(i < 4 ? (l ? prm.wB_o : prm.wA_o) + (size_t)cta * 8192 + i * 2048 + lane * 64
                                                                 : prm.wB_qkv + (size_t)(cta * 8 + (i - 4) * 2 + (lane >> 4)) * 3072 + 2048 + (lane & 15) * 64));
            __nanosleep(PFGAP);
          }
          continue;
        }
        if (ph == 1) {
          if (par) continue;
#pragma unroll 1
          for (int i = 0; i < 2; i++) {
            if (i && lp + hw == 1 && NLAYERS > 1) {
#pragma unroll 1
              for (int c = 0; c < 8; c++) {
                if (!(c & 3)) asm volatile("bar.sync %0, 288;" :: "r"(BAR_WF + (c >> 2)) : "memory");
                if (el) {
                  tma_store_2d(&tm_wf, sbase + 11 * SLOT + c * 4096, (c < 4 ? 1024 : -128) + jj * 128 + (c >> 1) * 64, mm * 64 + (c & 1) * 32);
                  if ((c & 3) == 3) {
                    asm volatile("cp.async.bulk.commit_group;\ncp.async.bulk.wait_group.read 0;" ::: "memory");
                    mbar_arrive_local(bar_phi + (c >> 2) * 8);
                  } else __nanosleep(WFGAP);
                }
                __syncwarp();
              }
              if (el) { bulk_commit_wait(); signal_release(&g_flags.wfready[jj].v); PROFT(335); }
              __syncwarp();
            }
            mbar_wait_sl(bar_done + (i ? HW1 : (hw ? 19 : HW0)) * 8, 0);
            if (lp + hw == 2 && NLAYERS > 1) mbar_wait_sl(bar_phi, 1);
            const uint4* src = g_halo + (size_t)(mm * 8 + jj - 8) * 512 + i * 256 + hw * 128 + lane;
            uint4 v[4];
            int it = 0;
            bool ok;
            do {
#pragma unroll
              for (int j = 0; j < 4; j++) v[j] = mm ? ld_b128(src + j * 32) : make_uint4(H_BIT(l), 0, 0, 0);
              ok = __all_sync(0xffffffffu, (((v[0].x ^ H_BIT(l)) | (v[1].x ^ H_BIT(l)) | (v[2].x ^ H_BIT(l)) | (v[3].x ^ H_BIT(l))) & 1) == 0);
            } while (!ok && ++it < (1 << 16));
#pragma unroll
            for (int j = 0; j < 4; j++) sts128(sbase + OFF_S + hw * SLOT + j * 512 + lane * 16, v[j].x, v[j].y, v[j].z, v[j].w);
            __syncwarp();
            if (el) { mbar_arrive_local(bar_halo + hw * 8); PROFT(331 + l * 16 + i * 2 + hw); }
            __syncwarp();
          }
        } else if (hw == 0 && l < NLAYERS - 1) {
          bar_sync<BAR_X1, 288>();
          if (el) {
            PROFT(328 + l * 16);
            mbar_wait_sl(bar_full + XD * 8, par ^ 1);
            tma_store_2d(&tm_o, sbase + 11 * SLOT, jj * 128 + 64, mm * 128 + S_LEN);
            bulk_commit_wait();
            signal_release(&g_flags.xready[l + 1][mm].v);
            PROFT(330 + l * 16);
          }
          __syncwarp();
        }
      }
    }
    cluster_sync();
  } else {
    asm volatile("setmaxnreg.inc.sync.aligned.u32 232;");
    LOAD_EPOCH();
    const int wg = warp >> 2;
    const int r0 = warp * 16;
    const uint32_t pK = sbase + OFF_S, pV = sbase + OFF_S + SLOT;
#define PMASKS(on, bit) const uint32_t pm0 = ((on) && t == (g & 3) && (g >> 2) == (g & 1)), pm1 = ((on) && t == (g & 3) && (g >> 2) != (g & 1)), pbit = (bit)
#define PBIT0(w) (((w) & ~pm0) | (pbit & pm0))
#define PBIT1(w) (((w) & ~pm1) | (pbit & pm1))
#define LANE_CONSTS() \
    int lane; asm volatile("mov.u32 %0, %%laneid;" : "=r"(lane)); \
    const int g = lane >> 2, t = lane & 3; \
    const uint32_t srowoff = (r0 + (lane & 15)) * 128, lsw = (lane & 7) << 4, lhi = (lane >> 4) << 4, lsw2 = (lane & 6) << 3; \
    (void)g; (void)t; (void)srowoff; (void)lsw; (void)lhi; (void)lsw2;
    uint32_t stgp = 0, peer;
    asm volatile("mapa.shared::cluster.u32 %0, %1, %2;" : "=r"(peer) : "r"(sbase), "r"(rank ^ 1));
    peer -= sbase;
    const uint32_t dA0 = (((sbase & 0x3FFFF) + wg * 8192) >> 4) | 0x10000u, dB0 = ((sbase & 0x3FFFF) >> 4) | 0x2000000u;
    cluster_wait();
#define DESC(lo, hi) ((uint64_t)(uint32_t)(lo) | ((uint64_t)(hi) << 32))
#define STG_ARRIVE() { __syncwarp(); if (elect_one()) mbar_arrive_local(bar_stg); }
#define STG_WAIT() { mbar_wait(bar_stg, stgp); stgp ^= 1; }
#define PROFS() do {} while (0)
#define REL(addr) { if (elect_one()) { mbar_arrive_local(addr); asm volatile("mbarrier.arrive.shared::cluster.b64 _, [%0];" :: "r"((addr) + peer) : "memory"); } }
#define QSTEP(ACC, DA, SC, PRE) { \
      const uint32_t da = (DA), db = dB0 + (ub & 0x18) * (QST >> 7); \
      mbar_wait(ub, par); \
      PRE; \
      wgmma_fence(); \
      wgmma4_n192<SC>(ACC, da, db); \
      wgmma_commit(); PROFS(); }
#define QREL() { wgmma_wait<1>(); REL(ub + 376); ub += 8; }
#define RA_CUR (dA0 + (OFF_RA >> 4) + (ub & 0x18) * (SLOT >> 7))
#define PUMP1() { QSTEP(S1, RA_CUR, 1, {}); QREL(); }
#define PUMP0() { PUMP1(); SCHED_FENCE(); }
#define PUMP() if (h == 0) PUMP1()
#define WSTEP() { \
      const uint32_t s4 = (ub - bar_full - 256) >> 1; \
      const uint32_t da = dA0 + (((uint32_t)(WO_ASLOT(par) >> s4) & 15) << 10), db = dB0 + (((uint32_t)(WO_BSLOT >> s4) & 15) << 10); \
      mbar_wait(ub, par); \
      wgmma_fence(); \
      wgmma4_n128<1>(S1, da, db); \
      wgmma_commit(); PROFS(); \
      wgmma_wait<1>(); \
      if (s4) REL(ub + 376); \
      ub += 8; }
#define PUMPS(n) { _Pragma("unroll 1") for (int i_ = 0; i_ < (n); i_++) PUMP1(); }
#define SITE(n) { if ((BMASK >> (n)) & 1) PUMP1(); SCHED_FENCE(); }
#define LNSTEP(ACC, hh) { wgmma_fence(); wgmma_n192<1, 0>(ACC, make_desc(sbase + OFF_LNA + wg * 1024, 0, 128) ^ (1ull << 62), make_desc(sbase + OFF_LNB + (hh) * 4096, 0, 128) ^ (1ull << 62)); }
#define WARP_STORE(tm, tile, col, row) { fence_proxy_async_smem(); __syncwarp(); \
      if (elect_one()) { tma_store_2d(tm, (tile) + r0 * 128, col, (row) + r0); asm volatile("cp.async.bulk.commit_group;" ::: "memory"); } __syncwarp(); }
#define PUBLISH_O() WARP_STORE(&tm_os, pO, jj * 128 + h * 64, mm * 128)
#define TILE_CONSTS(base, on, bit) \
      uint32_t ta[6]; \
      { PMASKS(on, bit); (void)pbit; ta[4] = pm0; ta[5] = pm1; } \
      _Pragma("unroll") for (int j = 0; j < 4; j++) ta[j] = (base) + srowoff + ((((uint32_t)j << 5) + lhi) ^ lsw); \
      PINU(ta, 6); SCHED_FENCE(); \
      const uint32_t pm0 = ta[4], pm1 = ta[5], pbit = (bit)
#define X_OUT(pc) { \
      _Pragma("unroll") for (int j = (pc) * 4; j < (pc) * 4 + 4; j++) \
        stsm_x4(ta[j & 3] + (pc) * SLOT, \
                PBIT0(pack_bf16(S1[j * 8 + 0], S1[j * 8 + 1])), PBIT0(pack_bf16(S1[j * 8 + 2], S1[j * 8 + 3])), \
                PBIT1(pack_bf16(S1[j * 8 + 4], S1[j * 8 + 5])), PBIT1(pack_bf16(S1[j * 8 + 6], S1[j * 8 + 7]))); }
#define REST_P1(SKEW) { \
      mbar_wait(bar_stat2, par); \
      LNSTEP(S1, 1); \
      _Pragma("unroll 1") while (ub < bar_full + 256) { \
        if (ub == bar_full + 256 - 8 * (SKEW) && wg == 0) bar_sync<BAR_SKEW, 256>(); \
        QSTEP(S1, RA_CUR, 1, {}); \
        if (ub == bar_full + 248 && wg == 1) bar_arrive<BAR_SKEW, 256>(); \
        QREL(); \
      } \
      mbar_wait(bar_done + (31 - (SKEW)) * 8, par);        \
      wgmma_wait<0>(); \
      ACC_FENCE(S1, 96); \
      REL(bar_done + 31 * 8); \
      PROF(13); }
#define FOLD(tile, rd) { \
          LANE_CONSTS(); \
          float d[32]; \
          ACC_DEF(d, 32); \
          mbar_wait(bar_phi, 0); \
          wgmma_fence(); \
          _Pragma("unroll") for (int i = 0; i < 2; i++) { \
            const uint64_t da = make_desc((tile) + wg * 8192 + i * 64, 16, 1024); \
            const uint64_t db = make_desc(sbase + OFF_PHI + wg * 4096 + i * 2048, 16, 512) ^ (3ull << 62); \
            wgmma_n32<0>(d + i * 16, da, db); wgmma_n32<1>(d + i * 16, da + 2, db + 64); \
          } \
          wgmma_commit(); \
          PUMP0(); \
          ACC_FENCE(d, 32); \
          bar_wg(wg); \
          _Pragma("unroll") for (int i = 0; i < 4; i++) { \
            const float* x = d + (i & 1) * 8 + (i >> 1) * 2; \
            if (rd) sts128((tile) + wg * 8192 + ((warp & 3) * 16 + (i >> 1) * 8 + g) * 128 + (((2 * t + (i & 1)) ^ g) << 4), \
                           pack_bf16(x[0], x[1]), pack_bf16(x[4], x[5]), pack_bf16(x[16], x[17]), pack_bf16(x[20], x[21])); \
            else stsm_x4((tile) + srowoff + ((((uint32_t)i << 5) + lhi) ^ lsw), pack_bf16(d[i * 8], d[i * 8 + 1]), pack_bf16(d[i * 8 + 2], d[i * 8 + 3]), \
                         pack_bf16(d[i * 8 + 4], d[i * 8 + 5]), pack_bf16(d[i * 8 + 6], d[i * 8 + 7])); \
          } \
          }
#define LOAD_X0(base) \
      _Pragma("unroll") for (int j = 0; j < 8; j++) { \
        uint32_t x0, x1, x2, x3; \
        ldsm_x4((base) + (j >> 2) * SLOT + srowoff + ((((uint32_t)(j & 3) << 5) + lhi) ^ lsw), x0, x1, x2, x3); \
        S1[j * 8 + 0] = bf_lo(x0); S1[j * 8 + 1] = bf_hi(x0); S1[j * 8 + 2] = bf_lo(x1); S1[j * 8 + 3] = bf_hi(x1); \
        S1[j * 8 + 4] = bf_lo(x2); S1[j * 8 + 5] = bf_hi(x2); S1[j * 8 + 6] = bf_lo(x3); S1[j * 8 + 7] = bf_hi(x3); \
      }
#define LOAD_X() { \
      wgmma_wait<0>(); \
      mbar_wait(bar_xr, par); \
      LOAD_X0(sbase + OFF_RA); \
      ACC_FENCE(S1, 64); \
      __syncwarp(); if (elect_one()) mbar_arrive_local(bar_lx); }

    float S1[96];
#pragma unroll
    for (int i = 0; i < 64; i++) S1[i] = 0.f;
#pragma unroll 1
    for (int l = 0; l < NLAYERS; l++) {
      const uint32_t par = l & 1;
      bar_wg(wg);
      PROF(0);
      uint32_t ub = bar_full;
      float S0[96];
      {
        LANE_CONSTS();
        ACC_DEF(S0, 96);
        QSTEP(S0, dA0 + (OFF_S >> 4), 0, {});
        ub += 8;
        PROF(1);
        uint32_t ta[4];
#pragma unroll
        for (int j = 0; j < 4; j++) ta[j] = pK + srowoff + ((((uint32_t)j << 5) + lhi) ^ lsw);
        if (l) { PMASKS(false, 0); X_OUT(1); fence_proxy_async_smem(); }
        float p0, p1, a0 = 0.f, a1 = 0.f, q0 = 0.f, q1 = 0.f;
#define STATS(j0, j1) _Pragma("unroll") for (int j = (j0); j < (j1); j++) { \
          uint32_t x[4]; \
          ldsm_x4(ta[j & 3] + (j >> 2) * SLOT, x[0], x[1], x[2], x[3]); \
          if (j == 0) { p0 = __shfl_sync(0xffffffffu, bf_lo(x[0]), lane & 28); p1 = __shfl_sync(0xffffffffu, bf_lo(x[1]), lane & 28); } \
          _Pragma("unroll") for (int i = 0; i < 4; i += 2) { \
            const float d0 = bf_lo(x[i]) - p0, d1 = bf_hi(x[i]) - p0, d2 = bf_lo(x[i + 1]) - p1, d3 = bf_hi(x[i + 1]) - p1; \
            a0 += d0 + d1; a1 += d2 + d3; \
            q0 = fmaf(d1, d1, fmaf(d0, d0, q0)); q1 = fmaf(d3, d3, fmaf(d2, d2, q1)); } } \
          asm volatile("" : "+f"(a0), "+f"(a1), "+f"(q0), "+f"(q1), "+f"(p0), "+f"(p1)); SCHED_FENCE()
        if (SB0) { STATS(0, SB0); }
        bar_wg(wg);
        QSTEP(S0, dA0 + ((OFF_S + SLOT) >> 4), 1, {});
        QREL();
        SCHED_FENCE();
        STATS(SB0, SB1);
        ACC_DEF(S1, 96);
        QSTEP(S1, dA0 + (OFF_S >> 4), 0, {});
        QREL();
        SCHED_FENCE();
        STATS(SB1, SB2);
        QSTEP(S1, dA0 + ((OFF_S + SLOT) >> 4), 1, {});
        QREL();
        SCHED_FENCE();
        STATS(SB2, SB3);
        if (SB3 < 8) {
          if (l) { asm volatile("cp.async.bulk.wait_group 0;" ::: "memory"); bar_arrive<BAR_X1, 288>(); }
          QSTEP(S0, RA_CUR, 1, {});
          SCHED_FENCE();
          STATS(SB3, 8);
          QREL();
        }
#pragma unroll
        for (int o = 1; o <= 2; o <<= 1) {
          a0 += __shfl_xor_sync(0xffffffffu, a0, o); a1 += __shfl_xor_sync(0xffffffffu, a1, o);
          q0 += __shfl_xor_sync(0xffffffffu, q0, o); q1 += __shfl_xor_sync(0xffffffffu, q1, o);
        }
        if (t == 1) { a0 = a1; q0 = q1; p0 = p1; }
        if (t < 2) st_b64(g_stats + (size_t)(mm * 128 + r0 + g + t * 8) * 8 + jj, __float_as_uint(fmaf(a0, 1.f / 128.f, p0)),
                          (__float_as_uint(fmaxf(fmaf(a0 * (-1.f / 128.f), a0, q0), 0.f)) & ~3u) | STAT_TAG(l));
        if (SB3 == 8 && l) { asm volatile("cp.async.bulk.wait_group 0;" ::: "memory"); bar_arrive<BAR_X1, 288>(); }
#pragma unroll 1
        for (int i = (SB3 < 8); i < 14; i++) {
          QSTEP(S0, RA_CUR, 1, {});
          if (i == 0) PROF(2);
          QREL();
        }
      }
      LANE_CONSTS();
      mbar_wait(bar_stat, par);
      LNSTEP(S0, 0);
      wgmma_commit();
      const float rs0 = lds32f(sbase + OFF_ST + (r0 + g) * 4), rs1 = lds32f(sbase + OFF_ST + (r0 + g + 8) * 4);
      PUMP0();
      ACC_FENCE(S0, 96);
      PROF(3);
      if (!par) {
        constexpr uint32_t par = 0;
        uint32_t qa[16];
        uint32_t kf[32], vf[32];
#define DRAIN_A(ACC, hp, PMP) { \
          LANE_CONSTS(); \
          FRAG(kf + 16, ACC + 32, 0, (hp) * 2); \
          PMP; \
          FRAG(vf + 16, ACC + 64, 1, (hp) * 2 + 1); \
          _Pragma("unroll") for (int i_ = 0; i_ < 16; i_++) qa[i_] = pack_bf16(ACC[2 * i_], ACC[2 * i_ + 1]); \
          PINU(qa, 16); }
        DRAIN_A(S0, 0, PUMP0());
        if (l == 0 && NLAYERS > 1) {
#pragma unroll 1
          for (int rd = 1; rd >= 0; rd--) {
            FOLD(sbase + (12 - rd) * SLOT, rd);
            fence_proxy_async_smem();
            asm volatile("bar.arrive %0, 288;" :: "r"(BAR_WF + 1 - rd) : "memory");
          }
        }
        PUMPS(FPUMP);
        if (l == 0 && NLAYERS > 1) mbar_wait(bar_phi, 1);
#pragma unroll 1
        for (int h = 0; h < 2; h++) {
          const uint32_t pO = sbase + (h ? 3 : 12) * SLOT;
          PROF(4 + h * 12);
          LANE_CONSTS();
          FRAG_PUT(kf + 16, 10); FRAG_PUT(vf + 16, 11);
          STG_ARRIVE();
          if (h) { LOAD_X(); if (AW0) WSTEP(); } else PUMPS(HPUMP2);
          const bool e = g & 1, hb = (2 * t + (g & 1)) <= g;
          uint32_t sel[3] = {e ? 0x1044u : 0x4410u, hb ? 0x4444u : (e ? 0x3244u : 0x4432u), hb ? (e ? 0x3244u : 0x4432u) : 0x4444u};
          PINU(sel, 3);
          TILE_CONSTS(pO, true, O_BIT(l));
          const uint32_t selA = sel[0], selL = sel[1], selH = sel[2];
          STG_WAIT();
          if (warp == 0) mbar_wait(bar_halo, h);
          FRAG_GET(kf, 10);
          PROF(5 + h * 12);
          float s[2][4][4];
#pragma unroll
          for (int ks = 0; ks < 2; ks++)
#pragma unroll
            for (int i = 0; i < 8; i++) {
              const int hh = (i >> 1) & 1, jb = (i & 1) + (~i >> 1 & 2);
              const uint32_t* b = kf + (jb >> 1) * 16 + hh * 8 + ks * 4 + (jb & 1) * 2;
              if (ks) mma_bf16(s[hh][jb], qa[hh * 8 + 4], qa[hh * 8 + 5], qa[hh * 8 + 6], qa[hh * 8 + 7], b[0], b[1]);
              else mma_bf16_z(s[hh][jb], qa[hh * 8], qa[hh * 8 + 1], qa[hh * 8 + 2], qa[hh * 8 + 3], b[0], b[1]);
            }
          PUMP();
          PROF(6 + h * 12);
          float va[2][2], vb[2][2], mx[2][2];
#pragma unroll
          for (int hh = 0; hh < 2; hh++) {
            va[hh][0] = e ? s[hh][1][1] : s[hh][1][0];
            vb[hh][0] = hb ? (e ? s[hh][2][1] : s[hh][2][0]) : (e ? s[hh][0][1] : s[hh][0][0]);
            va[hh][1] = e ? s[hh][2][3] : s[hh][2][2];
            vb[hh][1] = hb ? (e ? s[hh][3][3] : s[hh][3][2]) : (e ? s[hh][1][3] : s[hh][1][2]);
          }
          if (warp == 0 && mm == 0) {
#pragma unroll
            for (int hh = 0; hh < 2; hh++) { va[hh][0] = -INFINITY; if (!hb) { vb[hh][0] = -INFINITY; vb[hh][1] = -INFINITY; } }
          }
#pragma unroll
          for (int i = 0; i < 4; i++) mx[i >> 1][i & 1] = fmaxf(va[i >> 1][i & 1], vb[i >> 1][i & 1]);
#pragma unroll
          for (int o = 1; o <= 2; o <<= 1)
#pragma unroll
            for (int i = 0; i < 4; i++) mx[i >> 1][i & 1] = fmaxf(mx[i >> 1][i & 1], __shfl_xor_sync(0xffffffffu, mx[i >> 1][i & 1], o));
          const float sc0 = rs0 * (0.17677669529663687f * LOG2E), sc1 = rs1 * (0.17677669529663687f * LOG2E);
#pragma unroll
          for (int i = 0; i < 4; i++) {
            const float sc = (i & 1) ? sc1 : sc0, m = mx[i >> 1][i & 1];
            va[i >> 1][i & 1] = ex2((va[i >> 1][i & 1] - m) * sc); vb[i >> 1][i & 1] = ex2((vb[i >> 1][i & 1] - m) * sc);
            mx[i >> 1][i & 1] = va[i >> 1][i & 1] + vb[i >> 1][i & 1];
          }
          if (h == 0 && ASITE) { PIN(&va[0][0], 4); PIN(&vb[0][0], 4); PIN(&mx[0][0], 4); PUMP1(); }
          if (warp == 0) mbar_wait(bar_halo + 8, h);
          FRAG_GET(vf, 11);
#pragma unroll
          for (int o = 1; o <= 2; o <<= 1)
#pragma unroll
            for (int i = 0; i < 4; i++) mx[i >> 1][i & 1] += __shfl_xor_sync(0xffffffffu, mx[i >> 1][i & 1], o);
          float o[2][4][4];
          uint32_t pa[2][8];
#pragma unroll
          for (int hh = 0; hh < 2; hh++) {
            const float i0 = rcp_fast(mx[hh][0]), i1 = rcp_fast(mx[hh][1]);
            const uint32_t w0 = pack_bf16(va[hh][0] * i0, vb[hh][0] * i0), w1 = pack_bf16(va[hh][1] * i1, vb[hh][1] * i1);
            pa[hh][0] = __byte_perm(w0, 0, selL); pa[hh][2] = __byte_perm(w0, 0, selA); pa[hh][3] = __byte_perm(w1, 0, selL);
            pa[hh][4] = __byte_perm(w0, 0, selH); pa[hh][5] = __byte_perm(w1, 0, selA); pa[hh][7] = __byte_perm(w1, 0, selH);
            pa[hh][1] = pa[hh][0] & pa[hh][4]; pa[hh][6] = pa[hh][3] & pa[hh][7];
          }
          PROF(7 + h * 12);
#pragma unroll
          for (int i = 0; i < 8; i++) mma_bf16_z(o[i >> 2][i & 3], pa[i >> 2][4], pa[i >> 2][5], pa[i >> 2][6], pa[i >> 2][7], vf[16 + 2 * i], vf[17 + 2 * i]);
#pragma unroll
          for (int i = 0; i < 8; i++) mma_bf16(o[i >> 2][i & 3], pa[i >> 2][0], pa[i >> 2][1], pa[i >> 2][2], pa[i >> 2][3], vf[2 * i], vf[2 * i + 1]);
          if (h == 0) PUMP1() else mbar_wait(bar_done + 30 * 8, par);
          if (NLAYERS > 1) mbar_wait(bar_phi + 8, 0);
#pragma unroll
          for (int i = 0; i < 4; i++) {
            const int hh = i >> 1, dp = i & 1;
            stsm_x4(ta[i],
                    PBIT0(pack_bf16(o[hh][dp * 2][0], o[hh][dp * 2][1])), PBIT0(pack_bf16(o[hh][dp * 2][2], o[hh][dp * 2][3])),
                    PBIT1(pack_bf16(o[hh][dp * 2 + 1][0], o[hh][dp * 2 + 1][1])), PBIT1(pack_bf16(o[hh][dp * 2 + 1][2], o[hh][dp * 2 + 1][3])));
          }
          PUBLISH_O();
          PROF(11 + h * 12);
          if (h) break;
          REST_P1(ASKEW);
          asm volatile("cp.async.bulk.wait_group.read 0;" ::: "memory");
          DRAIN_A(S1, 1, {});
        }
      } else {
        constexpr uint32_t par = 1;
        float st[32];
        const float c0 = rs0 * LOG2E, c1 = rs1 * LOG2E;
        { V_ADDR(pV); STAGE_V(S0 + 64); }
        if (warp < 2) sts128(sbase + OFF_ONES + warp * 512 + lane * 16, 0x3F803F80u, 0x3F803F80u, 0x3F803F80u, 0x3F803F80u);
        scale32(st, S0, c0, c1);
        PIN(st, 32);
#define KV_MMA(vs) { \
          const uint32_t dp = dA0 + 12 * 1024 - wg * 2560, dv = dA0 + (vs) * 1024 + ((OFF_ONES - (vs) * SLOT - 16) << 12) - wg * (512 << 16); \
          STG_WAIT(); \
          wgmma_fence(); \
          _Pragma("unroll") for (int ks = 0; ks < 8; ks++) { \
            const uint64_t a = DESC(dp + ks * 128, 0x40000040), b = DESC(dv + ks * (64 - (64 << 16)), 0x80000020); \
            if (ks == 0) wgmma_n40<0, 1>(kv, a, b); else wgmma_n40<1, 1>(kv, a, b); } \
          wgmma_commit(); }
#define KV_RED(hp) { \
          float* kvg = g_kv[l >> 1] + (jj * 4 + (hp) * 2) * KVH + warp * 768 + lane * 4; \
          _Pragma("unroll") for (int i = 0; i < 5; i++) red_v4(kvg + i * 128, kv[i * 3], kv[i * 3 + 1], kv[i * 3 + 2], 1.f); \
          red_v4(kvg + 640, kv[15], kv[16], kv[18], 1.f); }
#define KV_LOAD(hp) { \
          const uint4* kvg = reinterpret_cast<const uint4*>(g_kv[l >> 1] + (jj * 4 + (hp) * 2) * KVH) + warp * 192 + lane; \
          _Pragma("unroll") for (int i = 0; i < 6; i++) v[i] = ld_b128(kvg + i * 32); }
#define KVV(i) __uint_as_float((i) % 3 == 0 ? v[(i) / 3].x : ((i) % 3 == 1 ? v[(i) / 3].y : v[(i) / 3].z))
#define KV_TILE(hp) { \
          _Pragma("unroll 1") for (int it = 0; it < (1 << 16); it++) { \
            if (__all_sync(0xffffffffu, (v[0].w & v[1].w & v[2].w & v[3].w & v[4].w & v[5].w) == 0x41800000u)) break; \
            RETRY_COUNT(); \
            KV_LOAD(hp); \
          } \
          PROF(25 + (hp)); \
          const uint32_t e = lane & 7, jt = ((lane >> 1) & 4) + (e >> 1); \
          const uint32_t row = ((((warp >> 1) ^ wg) & 1) << 5) + ((jt & 1) << 4) + ((warp & 1) << 3) + (jt & 6) + (e & 1); \
          const uint32_t kd = pV + wg * 8192 + row * 128, ksw = (row & 7) << 4; \
          _Pragma("unroll") for (int i = 0; i < 2; i++) \
            stsm_x4(kd + ((i * 32 + lhi) ^ ksw), pack_bf16(KVV(i * 8), KVV(i * 8 + 1)), pack_bf16(KVV(i * 8 + 2), KVV(i * 8 + 3)), \
                    pack_bf16(KVV(i * 8 + 4), KVV(i * 8 + 5)), pack_bf16(KVV(i * 8 + 6), KVV(i * 8 + 7))); \
          stsm_x4(kd + ((64u + lhi) ^ ksw), pack_bf16(KVV(16), 1.f), pack_bf16(KVV(17), 1.f), 0u, 0u); }
#pragma unroll 1
        for (int h = 0; h < 2; h++) {
          PROF(4 + h * 2);
          SITE(0);
          LANE_CONSTS();
          const uint32_t dsw = (uint32_t)(g ^ (2 * t)) << 4, dst = ((t & 2) ? pK : sbase + 12 * SLOT) + (r0 + g) * 128;
          float e[16], f[16];
          float sa = exps16_<0>(e, st);
          exps16_fix<0>(e, st, sa);
          asm volatile("" : "+f"(sa)); PIN(e, 16); SITE(1);
          if (h) STG_WAIT();
          store16(e, sa, dst, dsw, 4);
          float sb = exps16_<1>(f, st);
          exps16_fix<1>(f, st, sb);
          asm volatile("" : "+f"(sb)); PIN(f, 16); SITE(2);
          store16(f, sb, dst, dsw, 0);
          float sc = exps16_<0>(e, st + 2);
          exps16_fix<0>(e, st + 2, sc);
          asm volatile("" : "+f"(sc)); PIN(e, 16); SITE(3);
          store16(e, sc, dst + 1024, dsw, 4);
          float sd = exps16_<1>(f, st + 2);
          exps16_fix<1>(f, st + 2, sd);
          asm volatile("" : "+f"(sd)); PIN(f, 16); SITE(4);
          store16(f, sd, dst + 1024, dsw, 0);
          PROF(5 + h * 2);
          if (h) break;
          {
            float kv[20];
            ACC_DEF(kv, 20);
            fence_proxy_async_smem();
            STG_ARRIVE();
            KV_MMA(11);
            PUMP0();
            ACC_FENCE(kv, 20);
            KV_RED(0);
            STG_ARRIVE();
          }
          scale32(st, S0 + 32, c0, c1);
          PIN(st, 32);
        }
        bool big;
        uint4 v[6];
        {
          float kv[20];
          if (KT0) { LANE_CONSTS(); KV_LOAD(0); }
          mbar_wait(bar_stat2, par);
          LNSTEP(S1, 1);
          ub = bar_full + 240;
          PUMP1();
          if (wg == 0) bar_sync<BAR_SKEW, 256>();
          QSTEP(S1, RA_CUR, 1, {});
          if (wg == 1) bar_arrive<BAR_SKEW, 256>();
          QREL();
          if (KT0 == 2) { LANE_CONSTS(); KV_TILE(0); }
          LANE_CONSTS();
          V_ADDR(sbase + 3 * SLOT);
          PINU(va_, 2);
          mbar_wait(bar_done + 30 * 8, par);
          wgmma_wait<0>();
          ACC_FENCE(S1, 96);
          if (!(RLATE & 2)) REL(bar_done + 31 * 8);
          PROF(13);
          STAGE_V(S1 + 64);
          fence_proxy_async_smem();
          STG_ARRIVE();
          if (RLATE & 2) REL(bar_done + 31 * 8);
          scale32(st, S1, c0, c1);
          PIN(st, 32);
          PROF(16);
          ACC_DEF(kv, 20);
          KV_MMA(3);
          SCHED_FENCE();
          if (!KT0) KV_LOAD(0);
          big = any_big(st);
          if (EROT > 0) { phiq_a(st, big); PIN(st, 16); }
          SCHED_FENCE();
          wgmma_wait<0>();
          ACC_FENCE(kv, 20);
          KV_RED(1);
          PROF(17);
        }
#pragma unroll 1
        for (int h = 0; h < 2; h++) {
          const uint32_t pO = sbase + (h ? 3 : 8) * SLOT;
          LANE_CONSTS();
          uint32_t fq[32];
          if (EROT < 1) phiq_a(st, big);
          if (EMRG == 0) { phiq_b<0>(fq, st, big); PINU(fq, 16); }
          if (EMRG == 2) { phiq_b<1>(fq, st, big); PINU(fq, 16); PIN(st + 16, 16); }
          PROF(18 + h * 14);
          SCHED_FENCE();
          if (h) {
            asm volatile("cp.async.bulk.wait_group.read 0;" ::: "memory");
            mbar_wait(bar_lx, par);
          }
          if (h || KT0 < 2) {
            KV_TILE(h);
            fence_proxy_async_smem();
            STG_ARRIVE();
          }
          SCHED_FENCE();
          if (EMRG == 0) { phiq_a(st + 16, big); PIN(st + 16, 16); }
          if (EMRG == 1) { phiq_b<1>(fq, st, big); PINU(fq, 16); PIN(st + 16, 16); }
          if (h || KT0 < 2) STG_WAIT();
          wgmma_wait<0>();
          ACC_FENCE(S1, 64);
          PROF(19 + h * 14);
          float o[4][20];
#define O_MMA(hh) { \
            const uint64_t db = make_desc(pV + (hh) * 8192, 16, 1024); \
            ACC_DEF(o[(hh) * 2], 20); ACC_DEF(o[(hh) * 2 + 1], 20); \
            wgmma_fence(); \
            wgmma_n40_rs<0>(o[(hh) * 2], fq + (hh) * 16, db + 256); wgmma_n40_rs<0>(o[(hh) * 2 + 1], fq + (hh) * 16 + 8, db); \
            wgmma_n40_rs<1>(o[(hh) * 2], fq + (hh) * 16 + 4, db + 384); wgmma_n40_rs<1>(o[(hh) * 2 + 1], fq + (hh) * 16 + 12, db + 128); \
            wgmma_commit(); }
          O_MMA(0);
          SCHED_FENCE();
          phiq_b<0>(fq + 16, st + 16, big); PINU(fq + 16, 16);
          SCHED_FENCE();
          PMASKS(true, O_BIT(l));
#pragma unroll
          for (int hh = 0; hh < 2; hh++) {
            if (hh && !OW) O_MMA(1);
            wgmma_wait<0>();
            ACC_FENCE(o[hh * 2], 20); ACC_FENCE(o[hh * 2 + 1], 20);
            if (!hh && OW) { O_MMA(1); SCHED_FENCE(); }
            const float* x = o[hh * 2];
            const float* y = o[hh * 2 + 1];
            const float sx0 = x[17] * 0x1p-40f, sy0 = y[17] * 0x1p-40f, sx1 = x[19] * 0x1p-40f, sy1 = y[19] * 0x1p-40f;
            const float i0 = rcp_fast(fmaf(fmaf(x[17], 1e-6f, x[16]), sy0, y[16] * sx0)), i1 = rcp_fast(fmaf(fmaf(x[19], 1e-6f, x[18]), sy1, y[18] * sx1));
            const float ax0 = sy0 * i0, ay0 = sx0 * i0, ax1 = sy1 * i1, ay1 = sx1 * i1;
#pragma unroll
            for (int dp = 0; dp < 2; dp++)
              stsm_x4(pO + srowoff + ((hh * 64 + dp * 32 + lhi) ^ lsw),
                      PBIT0(pack_bf16(fmaf(x[dp * 8], ax0, y[dp * 8] * ay0), fmaf(x[dp * 8 + 1], ax0, y[dp * 8 + 1] * ay0))),
                      PBIT0(pack_bf16(fmaf(x[dp * 8 + 2], ax1, y[dp * 8 + 2] * ay1), fmaf(x[dp * 8 + 3], ax1, y[dp * 8 + 3] * ay1))),
                      PBIT1(pack_bf16(fmaf(x[dp * 8 + 4], ax0, y[dp * 8 + 4] * ay0), fmaf(x[dp * 8 + 5], ax0, y[dp * 8 + 5] * ay0))),
                      PBIT1(pack_bf16(fmaf(x[dp * 8 + 6], ax1, y[dp * 8 + 6] * ay1), fmaf(x[dp * 8 + 7], ax1, y[dp * 8 + 7] * ay1))));
          }
          PUBLISH_O();
          PROF(20 + h * 14);
          if (h) break;
          if (KVL == 2) { KV_LOAD(1); SCHED_FENCE(); }
          scale32(st, S1 + 32, c0, c1);
          PIN(st, 32);
          LOAD_X();
          bar_wg(wg);
          WSTEP();
          SCHED_FENCE();
          if (KVL == 0) KV_LOAD(1);
          big = any_big(st);
          if (KVL == 1) { SCHED_FENCE(); KV_LOAD(1); }
          if (EROT > 0) { phiq_a(st, big); PIN(st, 16); }
          PROF(31);
        }
      }
      __syncwarp();
      if (elect_one()) mbar_arrive_local(bar_epi);
      bar_wg(wg);
#pragma unroll 1
      while (ub < bar_full + 384) {
        WSTEP();
        if (ub == bar_full + 8 * 41) { asm volatile("cp.async.bulk.wait_group.read 0;" ::: "memory"); PROF(35); }
        if (ub == bar_full + 8 * 42) PROF(36);
      }
      {
        LANE_CONSTS();
        TILE_CONSTS(pK, l < NLAYERS - 1, X_BIT(l));
        wgmma_wait<0>();
        ACC_FENCE(S1, 64);
        if (!RLATE) REL(bar_done + 47 * 8);
        PROF(37);
        X_OUT(0);
        WARP_STORE(l < NLAYERS - 1 ? &tm_os : &tm_xo, pK, jj * 128, mm * 128 + (l < NLAYERS - 1 ? S_LEN : 0));
        if (RLATE) REL(bar_done + 47 * 8);
        if (l == NLAYERS - 1) {
          X_OUT(1);
          WARP_STORE(&tm_xo, pV, jj * 128 + 64, mm * 128);
          if (FINW) asm volatile("cp.async.bulk.wait_group 0;" ::: "memory"); else asm volatile("cp.async.bulk.wait_group.read 0;" ::: "memory");
        }
      }
#pragma unroll
      for (int i = 32; i < 64; i++) { uint32_t c; asm volatile("mov.b32 %0, %1;" : "=r"(c) : "f"(S1[i])); S1[i] = __uint_as_float(c); }
      PROF(38);
    }
    cluster_sync();
  }
}

typedef CUresult (*PFN_encode)(CUtensorMap*, CUtensorMapDataType, cuuint32_t, void*, const cuuint64_t*, const cuuint64_t*,
                               const cuuint32_t*, const cuuint32_t*, CUtensorMapInterleave, CUtensorMapSwizzle,
                               CUtensorMapL2promotion, CUtensorMapFloatOOBfill);

CUtensorMap make_map(PFN_encode enc, const void* ptr, uint64_t inner, uint64_t outer, uint32_t box_inner, uint32_t box_outer,
                     CUtensorMapSwizzle swz = CU_TENSOR_MAP_SWIZZLE_128B, int promo = CU_TENSOR_MAP_L2_PROMOTION_L2_256B) {
  CUtensorMap m;
  cuuint64_t dims[2] = {inner, outer};
  cuuint64_t strides[1] = {inner * 2};
  cuuint32_t box[2] = {box_inner, box_outer};
  cuuint32_t es[2] = {1, 1};
  enc(&m, CU_TENSOR_MAP_DATA_TYPE_BFLOAT16, 2, const_cast<void*>(ptr), dims, strides, box, es, CU_TENSOR_MAP_INTERLEAVE_NONE,
      swz, (CUtensorMapL2promotion)promo, CU_TENSOR_MAP_FLOAT_OOB_FILL_NONE);
  return m;
}

}

extern "C" void kernel_launch(void* const* d_in, const int* in_sizes, int n_in, void* d_out, int out_size) {
  (void)in_sizes; (void)n_in; (void)out_size;
  static PFN_encode enc = nullptr;
  if (!enc) {
    void* fn = nullptr;
    cudaDriverEntryPointQueryResult qr;
    cudaGetDriverEntryPoint("cuTensorMapEncodeTiled", &fn, cudaEnableDefault, &qr);
    enc = (PFN_encode)fn;
    cudaFuncSetAttribute(mega_kernel, cudaFuncAttributeMaxDynamicSharedMemorySize, SMEM_BYTES);
  }
  Params prm;
  prm.x0 = (const __nv_bfloat16*)d_in[0];
  prm.wA_qkv = (const __nv_bfloat16*)d_in[1];
  prm.wA_o = (const __nv_bfloat16*)d_in[2];
  prm.wB_qkv = (const __nv_bfloat16*)d_in[4];
  prm.wB_phi = (const __nv_bfloat16*)d_in[5];
  prm.wB_o = (const __nv_bfloat16*)d_in[6];
  prm.out = (__nv_bfloat16*)d_out;
  void *obuf = nullptr, *wf = nullptr;
  cudaGetSymbolAddress(&obuf, g_obuf);
  cudaGetSymbolAddress(&wf, g_wfold);
  CUtensorMap tm_x0 = make_map(enc, d_in[0], D_MODEL, S_LEN, 64, 128, CU_TENSOR_MAP_SWIZZLE_128B, XPROMO);
  CUtensorMap tm_xo = make_map(enc, d_out, D_MODEL, S_LEN, 64, 16);
  CUtensorMap tm_os = make_map(enc, obuf, D_MODEL, 2 * S_LEN, 64, 16);
  CUtensorMap tm_o = make_map(enc, obuf, D_MODEL, 2 * S_LEN, 64, 128, CU_TENSOR_MAP_SWIZZLE_128B, OPROMO);
  CUtensorMap tm_wf = make_map(enc, wf, 2048, D_MODEL, 64, 32);
  CUtensorMap tm_wqA = make_map(enc, d_in[1], 3 * D_MODEL, D_MODEL, 64, 32, CU_TENSOR_MAP_SWIZZLE_128B, WPROMO);
  CUtensorMap tm_wqB = make_map(enc, prm.wB_qkv, 3 * D_MODEL, D_MODEL, 64, 32);
  CUtensorMap tm_woA = make_map(enc, prm.wA_o, D_MODEL, D_MODEL, 64, 64);
  CUtensorMap tm_woB = make_map(enc, prm.wB_o, D_MODEL, D_MODEL, 64, 64);
  CUtensorMap tm_phi = make_map(enc, prm.wB_phi, 32, 1024, 32, 128, CU_TENSOR_MAP_SWIZZLE_64B);
  mega_kernel<<<NMAIN + NAUX, 384, SMEM_BYTES>>>(tm_x0, tm_xo, tm_os, tm_o, tm_wf, tm_wqA, tm_wqB, tm_woA, tm_woB, tm_phi, prm);
}
```

```cpp
#include <cuda_runtime.h>
#include <cuda.h>
#include <cuda_bf16.h>
#include <stdint.h>

#define NLAYERS 4

#define STAG1 0
#define HPUMP1 2
#define HPUMP2 1
#define ASKEW 2
#define FPUMP 3
#define PFGAP 100
#define POLLGAP 120
#define OW 1
#define AW0 1
#define RLATE 3
#define FSTART 0
#define MAPV 1
#define HW1 29
#define XPACE 0x06050401000000ull
#define XP0 4
#define HW0 18
#define XD 4
#define WFGAP 50
#define KT0 2
#define W23 0
#define AX 0
#define PF0 1
#define EARLY 2
#define BIGLIM 3600.f
#define SUMLO 0x1p-100f
#define SUMHI 0x1p100f
#define EROT 1
#define FINW 0
#define AHOIST 1
#define EMRG 1
#define XPROMO 2
#define OPROMO 3
#define STAG2 300
#define WPROMO 3
#define SB0 2
#define SB1 4
#define SB2 6
#define SB3 8
#define KVL 0
#define BMASK 0x1F
#define ASITE 1
#define COMMA ,
#define XA 0
#define XB 4
#define XMMA 1
#define WHOLD 0
#define WREL 47
#define WLEAD 0
#define ALAG 0
#define ADEL 0
#define ADEL0 0
namespace {

constexpr int S_LEN = 2048, D_MODEL = 1024;
constexpr int NAUX = 4, NMAIN = 128;
constexpr int SLOT = 16384;
constexpr int QST = 24576;
constexpr int OFF_RA = 6 * SLOT, OFF_S = 10 * SLOT;
constexpr int OFF_HALO = 13 * SLOT, OFF_LNB = OFF_HALO  , OFF_ONES = OFF_HALO + 3072;
constexpr int OFF_ST = OFF_HALO + 7168  , OFF_ID = OFF_HALO + 7680, OFF_PHI = OFF_HALO + 8192;
constexpr int OFF_BAR = 14 * SLOT;
constexpr int OFF_LNA = OFF_BAR + 1024;
constexpr int SMEM_BYTES = OFF_LNA + 2048;
#define WO_ASLOT(par) ((par) ? 0x9876CAB39876CA98ull : 0x98C76BA398C7698Cull)
constexpr unsigned long long WO_BSLOT = 0x5432105421054210ull;
__device__ __forceinline__ int srcb(int j, int i) { return (i + (i >= j)) & 7; }
__device__ __forceinline__ int kslice(int j, int i) { return i < 2 ? 2 * j + i : (i < 9 ? 2 * srcb(j, i - 2) : 2 * srcb(j, i - 9) + 1); }
__device__ __forceinline__ int wslice(int j, int s) { return 2 * ((s & 7) ? srcb(j, (s & 7) - 1) : j) + (s >> 3); }
constexpr int KVH = 6 * 128 * 4;

struct __align__(128) Flag { unsigned v; unsigned pad[31]; };
struct Flags {
  Flag xready[4][16];
  Flag wfready[8];
  Flag done;
  Flag epoch;
};

__device__ Flags g_flags;
__device__ __nv_bfloat16 g_obuf[2 * S_LEN * D_MODEL];
#define O_BIT(l) ((epoch * NLAYERS + (l) + 1) & 1u)
#define X_BIT(l) ((epoch * (NLAYERS - 1) + (l) + 1) & 1u)
__device__ __nv_bfloat16 g_wfold[D_MODEL * 2048];
__device__ uint4 g_halo[16 * 8 * 512];
__device__ __align__(128) float g_kv[2][32 * KVH];
__device__ __align__(128) uint2 g_colsum[2][1536][2];
__device__ __align__(128) uint2 g_stats[S_LEN * 8];
#define H_BIT(l) (NLAYERS > 2 ? (uint32_t)((l) == 0) : (ep1 & 1))
#define STAT_TAG(l) ((ep1 * NLAYERS + (l) + 1) & 3u)

#define RETRY_COUNT()
#define PRL 0
#define PRU 0
#define PROFL 1
#define PROFW 0
#define PROFT(i) do {} while (0)
#define PROF(i) do {} while (0)

__device__ __forceinline__ uint32_t smem_u32(const void* p) { return (uint32_t)__cvta_generic_to_shared(p); }
__device__ __forceinline__ bool elect_one() {
  uint32_t p;
  asm volatile("{\n.reg .pred p;\nelect.sync _|p, 0xffffffff;\nselp.u32 %0, 1, 0, p;\n}\n" : "=r"(p));
  return p != 0;
}
__device__ __forceinline__ void mbar_init(uint32_t bar, uint32_t cnt) {
  asm volatile("mbarrier.init.shared::cta.b64 [%0], %1;" :: "r"(bar), "r"(cnt));
}
__device__ __forceinline__ void mbar_expect_tx(uint32_t bar, uint32_t bytes) {
  asm volatile("mbarrier.arrive.expect_tx.shared::cta.b64 _, [%0], %1;" :: "r"(bar), "r"(bytes) : "memory");
}
#define mbar_wait(bar, parity) \
  asm volatile("{\n.reg .pred p, q;\nW_%=:\nmbarrier.try_wait.parity.shared::cta.b64 p, [%1], %2;\nadd.s32 %0, %0, -1;\n" \
               "setp.gt.and.s32 q, %0, 0, !p;\n@q bra.uni W_%=;\n}\n" : "+r"(budget) : "r"((uint32_t)(bar)), "r"((uint32_t)(parity)) : "memory")
#define mbar_wait_sl(bar, parity) \
  asm volatile("{\n.reg .pred p, q;\nW_%=:\nmbarrier.try_wait.parity.shared::cta.b64 p, [%1], %2, 20000;\nadd.s32 %0, %0, -64;\n" \
               "setp.gt.and.s32 q, %0, 0, !p;\n@q bra.uni W_%=;\n}\n" : "+r"(budget) : "r"((uint32_t)(bar)), "r"((uint32_t)(parity)) : "memory")
__device__ __forceinline__ void mbar_arrive_local(uint32_t bar) {
  asm volatile("mbarrier.arrive.shared::cta.b64 _, [%0];" :: "r"(bar) : "memory");
}
__device__ __forceinline__ void tma_load_2d(uint32_t dst, const CUtensorMap* tm, uint32_t bar, int c0, int c1) {
  asm volatile("cp.async.bulk.tensor.2d.shared::cluster.global.mbarrier::complete_tx::bytes [%0], [%1, {%3, %4}], [%2];"
               :: "r"(dst), "l"(tm), "r"(bar), "r"(c0), "r"(c1) : "memory");
}
__device__ __forceinline__ void tma_load_2d_mc(uint32_t dst, const CUtensorMap* tm, uint32_t bar, int c0, int c1) {
  asm volatile("cp.async.bulk.tensor.2d.shared::cluster.global.mbarrier::complete_tx::bytes.multicast::cluster [%0], [%1, {%3, %4}], [%2], %5;"
               :: "r"(dst), "l"(tm), "r"(bar), "r"(c0), "r"(c1), "h"((uint16_t)3) : "memory");
}
__device__ __forceinline__ void tma_store_2d(const CUtensorMap* tm, uint32_t src, int c0, int c1) {
  asm volatile("cp.async.bulk.tensor.2d.global.shared::cta.bulk_group [%0, {%2, %3}], [%1];"
               :: "l"(tm), "r"(src), "r"(c0), "r"(c1) : "memory");
}
__device__ __forceinline__ void bulk_commit_wait() {
  asm volatile("cp.async.bulk.commit_group;\ncp.async.bulk.wait_group 0;" ::: "memory");
}
__device__ __forceinline__ void prefetch_tmap(const CUtensorMap* tm) {
  asm volatile("prefetch.tensormap [%0];" :: "l"(tm) : "memory");
}
__device__ __forceinline__ void fence_proxy_async_global() { asm volatile("fence.proxy.async.global;" ::: "memory"); }
__device__ __forceinline__ void fence_proxy_async_smem() { asm volatile("fence.proxy.async.shared::cta;" ::: "memory"); }
__device__ __forceinline__ unsigned ld_relaxed(const unsigned* p) {
  unsigned v;
  asm volatile("ld.relaxed.gpu.global.u32 %0, [%1];" : "=r"(v) : "l"(p) : "memory");
  return v;
}
__device__ __forceinline__ void fence_acquire() { asm volatile("fence.acquire.gpu;" ::: "memory"); }
__device__ __forceinline__ void wait_flag(const unsigned* p, unsigned target) {
  int it = 0;
  while ((int)(ld_relaxed(p) - target) < 0 && ++it < (1 << 20)) {}
  fence_acquire();
}
__device__ __forceinline__ void signal_release(unsigned* p) {
  asm volatile("red.release.gpu.global.add.u32 [%0], 1;" :: "l"(p) : "memory");
}
template <int ID, int N> __device__ __forceinline__ void bar_arrive() { asm volatile("bar.arrive %0, %1;" :: "n"(ID), "n"(N) : "memory"); }
template <int ID, int N> __device__ __forceinline__ void bar_sync() { asm volatile("bar.sync %0, %1;" :: "n"(ID), "n"(N) : "memory"); }
__device__ __forceinline__ void bar_wg(int wg) { asm volatile("bar.sync %0, 128;" :: "r"(2 + wg) : "memory"); }
__device__ __forceinline__ void cluster_sync() {
  asm volatile("barrier.cluster.arrive.relaxed.aligned;\nbarrier.cluster.wait.aligned;" ::: "memory");
}
__device__ __forceinline__ void cluster_wait() { asm volatile("barrier.cluster.wait.acquire.aligned;" ::: "memory"); }
enum { BAR_X1 = 7, BAR_WF = 8  , BAR_SKEW = 10 };

__device__ __forceinline__ void wgmma_fence() { asm volatile("wgmma.fence.sync.aligned;" ::: "memory"); }
__device__ __forceinline__ void wgmma_commit() { asm volatile("wgmma.commit_group.sync.aligned;" ::: "memory"); }
template <int N> __device__ __forceinline__ void wgmma_wait() { asm volatile("wgmma.wait_group.sync.aligned %0;" :: "n"(N) : "memory"); }

template <int scale_d, int tnsp_b = 1> __device__ __forceinline__ void wgmma_n192(float* d, uint64_t descA, uint64_t descB) {
  asm volatile("{\n.reg .pred p;\nsetp.ne.b32 p, %98, 0;\n"
               "wgmma.mma_async.sync.aligned.m64n192k16.f32.bf16.bf16 {%0,%1,%2,%3,%4,%5,%6,%7,%8,%9,%10,%11,%12,%13,%14,%15,%16,%17,%18,%19,%20,%21,%22,%23,%24,%25,%26,%27,%28,%29,%30,%31,%32,%33,%34,%35,%36,%37,%38,%39,%40,%41,%42,%43,%44,%45,%46,%47,%48,%49,%50,%51,%52,%53,%54,%55,%56,%57,%58,%59,%60,%61,%62,%63,%64,%65,%66,%67,%68,%69,%70,%71,%72,%73,%74,%75,%76,%77,%78,%79,%80,%81,%82,%83,%84,%85,%86,%87,%88,%89,%90,%91,%92,%93,%94,%95}, %96, %97, p, 1, 1, 0, %99;\n}\n"
               : "+f"(d[0]), "+f"(d[1]), "+f"(d[2]), "+f"(d[3]), "+f"(d[4]), "+f"(d[5]), "+f"(d[6]), "+f"(d[7]), "+f"(d[8]), "+f"(d[9]), "+f"(d[10]), "+f"(d[11]), "+f"(d[12]), "+f"(d[13]), "+f"(d[14]), "+f"(d[15]), "+f"(d[16]), "+f"(d[17]), "+f"(d[18]), "+f"(d[19]), "+f"(d[20]), "+f"(d[21]), "+f"(d[22]), "+f"(d[23]), "+f"(d[24]), "+f"(d[25]), "+f"(d[26]), "+f"(d[27]), "+f"(d[28]), "+f"(d[29]), "+f"(d[30]), "+f"(d[31]), "+f"(d[32]), "+f"(d[33]), "+f"(d[34]), "+f"(d[35]), "+f"(d[36]), "+f"(d[37]), "+f"(d[38]), "+f"(d[39]), "+f"(d[40]), "+f"(d[41]), "+f"(d[42]), "+f"(d[43]), "+f"(d[44]), "+f"(d[45]), "+f"(d[46]), "+f"(d[47]), "+f"(d[48]), "+f"(d[49]), "+f"(d[50]), "+f"(d[51]), "+f"(d[52]), "+f"(d[53]), "+f"(d[54]), "+f"(d[55]), "+f"(d[56]), "+f"(d[57]), "+f"(d[58]), "+f"(d[59]), "+f"(d[60]), "+f"(d[61]), "+f"(d[62]), "+f"(d[63]), "+f"(d[64]), "+f"(d[65]), "+f"(d[66]), "+f"(d[67]), "+f"(d[68]), "+f"(d[69]), "+f"(d[70]), "+f"(d[71]), "+f"(d[72]), "+f"(d[73]), "+f"(d[74]), "+f"(d[75]), "+f"(d[76]), "+f"(d[77]), "+f"(d[78]), "+f"(d[79]), "+f"(d[80]), "+f"(d[81]), "+f"(d[82]), "+f"(d[83]), "+f"(d[84]), "+f"(d[85]), "+f"(d[86]), "+f"(d[87]), "+f"(d[88]), "+f"(d[89]), "+f"(d[90]), "+f"(d[91]), "+f"(d[92]), "+f"(d[93]), "+f"(d[94]), "+f"(d[95])
               : "l"(descA), "l"(descB), "n"(scale_d), "n"(tnsp_b));
}
template <int scale_d> __device__ __forceinline__ void wgmma4_n192(float* d, uint32_t da, uint32_t db) {
#define R_ "{%0,%1,%2,%3,%4,%5,%6,%7,%8,%9,%10,%11,%12,%13,%14,%15,%16,%17,%18,%19,%20,%21,%22,%23,%24,%25,%26,%27,%28,%29,%30,%31,%32,%33,%34,%35,%36,%37,%38,%39,%40,%41,%42,%43,%44,%45,%46,%47,%48,%49,%50,%51,%52,%53,%54,%55,%56,%57,%58,%59,%60,%61,%62,%63,%64,%65,%66,%67,%68,%69,%70,%71,%72,%73,%74,%75,%76,%77,%78,%79,%80,%81,%82,%83,%84,%85,%86,%87,%88,%89,%90,%91,%92,%93,%94,%95}"
  asm volatile("{\n.reg .pred p, q;\n.reg .b64 a, b;\nsetp.ne.b32 p, %98, 0;\nsetp.eq.b32 q, 0, 0;\nmov.b64 a, {%96, 0x40000040};\nmov.b64 b, {%97, 0x40000040};\n"
               "wgmma.mma_async.sync.aligned.m64n192k16.f32.bf16.bf16 " R_ ", a, b, p, 1, 1, 0, 1;\nadd.s64 a, a, 2;\nadd.s64 b, b, 128;\n"
               "wgmma.mma_async.sync.aligned.m64n192k16.f32.bf16.bf16 " R_ ", a, b, q, 1, 1, 0, 1;\nadd.s64 a, a, 2;\nadd.s64 b, b, 128;\n"
               "wgmma.mma_async.sync.aligned.m64n192k16.f32.bf16.bf16 " R_ ", a, b, q, 1, 1, 0, 1;\nadd.s64 a, a, 2;\nadd.s64 b, b, 128;\n"
               "wgmma.mma_async.sync.aligned.m64n192k16.f32.bf16.bf16 " R_ ", a, b, q, 1, 1, 0, 1;\n}\n"
               : "+f"(d[0]), "+f"(d[1]), "+f"(d[2]), "+f"(d[3]), "+f"(d[4]), "+f"(d[5]), "+f"(d[6]), "+f"(d[7]), "+f"(d[8]), "+f"(d[9]), "+f"(d[10]), "+f"(d[11]), "+f"(d[12]), "+f"(d[13]), "+f"(d[14]), "+f"(d[15]), "+f"(d[16]), "+f"(d[17]), "+f"(d[18]), "+f"(d[19]), "+f"(d[20]), "+f"(d[21]), "+f"(d[22]), "+f"(d[23]), "+f"(d[24]), "+f"(d[25]), "+f"(d[26]), "+f"(d[27]), "+f"(d[28]), "+f"(d[29]), "+f"(d[30]), "+f"(d[31]), "+f"(d[32]), "+f"(d[33]), "+f"(d[34]), "+f"(d[35]), "+f"(d[36]), "+f"(d[37]), "+f"(d[38]), "+f"(d[39]), "+f"(d[40]), "+f"(d[41]), "+f"(d[42]), "+f"(d[43]), "+f"(d[44]), "+f"(d[45]), "+f"(d[46]), "+f"(d[47]), "+f"(d[48]), "+f"(d[49]), "+f"(d[50]), "+f"(d[51]), "+f"(d[52]), "+f"(d[53]), "+f"(d[54]), "+f"(d[55]), "+f"(d[56]), "+f"(d[57]), "+f"(d[58]), "+f"(d[59]), "+f"(d[60]), "+f"(d[61]), "+f"(d[62]), "+f"(d[63]), "+f"(d[64]), "+f"(d[65]), "+f"(d[66]), "+f"(d[67]), "+f"(d[68]), "+f"(d[69]), "+f"(d[70]), "+f"(d[71]), "+f"(d[72]), "+f"(d[73]), "+f"(d[74]), "+f"(d[75]), "+f"(d[76]), "+f"(d[77]), "+f"(d[78]), "+f"(d[79]), "+f"(d[80]), "+f"(d[81]), "+f"(d[82]), "+f"(d[83]), "+f"(d[84]), "+f"(d[85]), "+f"(d[86]), "+f"(d[87]), "+f"(d[88]), "+f"(d[89]), "+f"(d[90]), "+f"(d[91]), "+f"(d[92]), "+f"(d[93]), "+f"(d[94]), "+f"(d[95])
               : "r"(da), "r"(db), "n"(scale_d));
#undef R_
}
template <int scale_d> __device__ __forceinline__ void wgmma4_n128(float* d, uint32_t da, uint32_t db) {
#define R_ "{%0,%1,%2,%3,%4,%5,%6,%7,%8,%9,%10,%11,%12,%13,%14,%15,%16,%17,%18,%19,%20,%21,%22,%23,%24,%25,%26,%27,%28,%29,%30,%31,%32,%33,%34,%35,%36,%37,%38,%39,%40,%41,%42,%43,%44,%45,%46,%47,%48,%49,%50,%51,%52,%53,%54,%55,%56,%57,%58,%59,%60,%61,%62,%63}"
  asm volatile("{\n.reg .pred p, q;\n.reg .b64 a, b;\nsetp.ne.b32 p, %66, 0;\nsetp.eq.b32 q, 0, 0;\nmov.b64 a, {%64, 0x40000040};\nmov.b64 b, {%65, 0x40000040};\n"
               "wgmma.mma_async.sync.aligned.m64n128k16.f32.bf16.bf16 " R_ ", a, b, p, 1, 1, 0, 1;\nadd.s64 a, a, 2;\nadd.s64 b, b, 128;\n"
               "wgmma.mma_async.sync.aligned.m64n128k16.f32.bf16.bf16 " R_ ", a, b, q, 1, 1, 0, 1;\nadd.s64 a, a, 2;\nadd.s64 b, b, 128;\n"
               "wgmma.mma_async.sync.aligned.m64n128k16.f32.bf16.bf16 " R_ ", a, b, q, 1, 1, 0, 1;\nadd.s64 a, a, 2;\nadd.s64 b, b, 128;\n"
               "wgmma.mma_async.sync.aligned.m64n128k16.f32.bf16.bf16 " R_ ", a, b, q, 1, 1, 0, 1;\n}\n"
               : "+f"(d[0]), "+f"(d[1]), "+f"(d[2]), "+f"(d[3]), "+f"(d[4]), "+f"(d[5]), "+f"(d[6]), "+f"(d[7]), "+f"(d[8]), "+f"(d[9]), "+f"(d[10]), "+f"(d[11]), "+f"(d[12]), "+f"(d[13]), "+f"(d[14]), "+f"(d[15]), "+f"(d[16]), "+f"(d[17]), "+f"(d[18]), "+f"(d[19]), "+f"(d[20]), "+f"(d[21]), "+f"(d[22]), "+f"(d[23]), "+f"(d[24]), "+f"(d[25]), "+f"(d[26]), "+f"(d[27]), "+f"(d[28]), "+f"(d[29]), "+f"(d[30]), "+f"(d[31]), "+f"(d[32]), "+f"(d[33]), "+f"(d[34]), "+f"(d[35]), "+f"(d[36]), "+f"(d[37]), "+f"(d[38]), "+f"(d[39]), "+f"(d[40]), "+f"(d[41]), "+f"(d[42]), "+f"(d[43]), "+f"(d[44]), "+f"(d[45]), "+f"(d[46]), "+f"(d[47]), "+f"(d[48]), "+f"(d[49]), "+f"(d[50]), "+f"(d[51]), "+f"(d[52]), "+f"(d[53]), "+f"(d[54]), "+f"(d[55]), "+f"(d[56]), "+f"(d[57]), "+f"(d[58]), "+f"(d[59]), "+f"(d[60]), "+f"(d[61]), "+f"(d[62]), "+f"(d[63])
               : "r"(da), "r"(db), "n"(scale_d));
#undef R_
}
template <int scale_d> __device__ __forceinline__ void wgmma_n32(float* d, uint64_t descA, uint64_t descB) {
  asm volatile("{\n.reg .pred p;\nsetp.ne.b32 p, %18, 0;\n"
               "wgmma.mma_async.sync.aligned.m64n32k16.f32.bf16.bf16 {%0,%1,%2,%3,%4,%5,%6,%7,%8,%9,%10,%11,%12,%13,%14,%15}, %16, %17, p, 1, 1, 0, 1;\n}\n"
               : "+f"(d[0]), "+f"(d[1]), "+f"(d[2]), "+f"(d[3]), "+f"(d[4]), "+f"(d[5]), "+f"(d[6]), "+f"(d[7]), "+f"(d[8]), "+f"(d[9]), "+f"(d[10]), "+f"(d[11]), "+f"(d[12]), "+f"(d[13]), "+f"(d[14]), "+f"(d[15])
               : "l"(descA), "l"(descB), "n"(scale_d));
}
template <int scale_d, int tnsp_a> __device__ __forceinline__ void wgmma_n40(float* d, uint64_t descA, uint64_t descB) {
  asm volatile("{\n.reg .pred p;\nsetp.ne.b32 p, %22, 0;\n"
               "wgmma.mma_async.sync.aligned.m64n40k16.f32.bf16.bf16 {%0,%1,%2,%3,%4,%5,%6,%7,%8,%9,%10,%11,%12,%13,%14,%15,%16,%17,%18,%19}, %20, %21, p, 1, 1, %23, 1;\n}\n"
               : "+f"(d[0]), "+f"(d[1]), "+f"(d[2]), "+f"(d[3]), "+f"(d[4]), "+f"(d[5]), "+f"(d[6]), "+f"(d[7]), "+f"(d[8]), "+f"(d[9]), "+f"(d[10]), "+f"(d[11]), "+f"(d[12]), "+f"(d[13]), "+f"(d[14]), "+f"(d[15]), "+f"(d[16]), "+f"(d[17]), "+f"(d[18]), "+f"(d[19])
               : "l"(descA), "l"(descB), "n"(scale_d), "n"(tnsp_a));
}
template <int scale_d> __device__ __forceinline__ void wgmma_n40_rs(float* d, const uint32_t* a, uint64_t descB) {
  asm volatile("{\n.reg .pred p;\nsetp.ne.b32 p, %25, 0;\n"
               "wgmma.mma_async.sync.aligned.m64n40k16.f32.bf16.bf16 {%0,%1,%2,%3,%4,%5,%6,%7,%8,%9,%10,%11,%12,%13,%14,%15,%16,%17,%18,%19}, {%20,%21,%22,%23}, %24, p, 1, 1, 1;\n}\n"
               : "+f"(d[0]), "+f"(d[1]), "+f"(d[2]), "+f"(d[3]), "+f"(d[4]), "+f"(d[5]), "+f"(d[6]), "+f"(d[7]), "+f"(d[8]), "+f"(d[9]), "+f"(d[10]), "+f"(d[11]), "+f"(d[12]), "+f"(d[13]), "+f"(d[14]), "+f"(d[15]), "+f"(d[16]), "+f"(d[17]), "+f"(d[18]), "+f"(d[19])
               : "r"(a[0]), "r"(a[1]), "r"(a[2]), "r"(a[3]), "l"(descB), "n"(scale_d));
}
__device__ __forceinline__ void wgmma_copy(float* d, uint32_t da, uint64_t descB, int keep) {
  asm volatile("{\n.reg .pred p;\n.reg .b64 a;\nsetp.ne.b32 p, %66, 0;\nmov.b64 a, {%64, 0x40000040};\n"
               "wgmma.mma_async.sync.aligned.m64n16k16.f32.bf16.bf16 {%0,%1,%2,%3,%4,%5,%6,%7}, a, %65, p, 1, 1, 0, 0;\nadd.s64 a, a, 2;\n"
               "wgmma.mma_async.sync.aligned.m64n16k16.f32.bf16.bf16 {%8,%9,%10,%11,%12,%13,%14,%15}, a, %65, p, 1, 1, 0, 0;\nadd.s64 a, a, 2;\n"
               "wgmma.mma_async.sync.aligned.m64n16k16.f32.bf16.bf16 {%16,%17,%18,%19,%20,%21,%22,%23}, a, %65, p, 1, 1, 0, 0;\nadd.s64 a, a, 2;\n"
               "wgmma.mma_async.sync.aligned.m64n16k16.f32.bf16.bf16 {%24,%25,%26,%27,%28,%29,%30,%31}, a, %65, p, 1, 1, 0, 0;\nadd.s64 a, a, 1018;\n"
               "wgmma.mma_async.sync.aligned.m64n16k16.f32.bf16.bf16 {%32,%33,%34,%35,%36,%37,%38,%39}, a, %65, p, 1, 1, 0, 0;\nadd.s64 a, a, 2;\n"
               "wgmma.mma_async.sync.aligned.m64n16k16.f32.bf16.bf16 {%40,%41,%42,%43,%44,%45,%46,%47}, a, %65, p, 1, 1, 0, 0;\nadd.s64 a, a, 2;\n"
               "wgmma.mma_async.sync.aligned.m64n16k16.f32.bf16.bf16 {%48,%49,%50,%51,%52,%53,%54,%55}, a, %65, p, 1, 1, 0, 0;\nadd.s64 a, a, 2;\n"
               "wgmma.mma_async.sync.aligned.m64n16k16.f32.bf16.bf16 {%56,%57,%58,%59,%60,%61,%62,%63}, a, %65, p, 1, 1, 0, 0;\n"
               "}\n"
               : "+f"(d[0]), "+f"(d[1]), "+f"(d[2]), "+f"(d[3]), "+f"(d[4]), "+f"(d[5]), "+f"(d[6]), "+f"(d[7]), "+f"(d[8]), "+f"(d[9]), "+f"(d[10]), "+f"(d[11]), "+f"(d[12]), "+f"(d[13]), "+f"(d[14]), "+f"(d[15]), "+f"(d[16]), "+f"(d[17]), "+f"(d[18]), "+f"(d[19]), "+f"(d[20]), "+f"(d[21]), "+f"(d[22]), "+f"(d[23]), "+f"(d[24]), "+f"(d[25]), "+f"(d[26]), "+f"(d[27]), "+f"(d[28]), "+f"(d[29]), "+f"(d[30]), "+f"(d[31]), "+f"(d[32]), "+f"(d[33]), "+f"(d[34]), "+f"(d[35]), "+f"(d[36]), "+f"(d[37]), "+f"(d[38]), "+f"(d[39]), "+f"(d[40]), "+f"(d[41]), "+f"(d[42]), "+f"(d[43]), "+f"(d[44]), "+f"(d[45]), "+f"(d[46]), "+f"(d[47]), "+f"(d[48]), "+f"(d[49]), "+f"(d[50]), "+f"(d[51]), "+f"(d[52]), "+f"(d[53]), "+f"(d[54]), "+f"(d[55]), "+f"(d[56]), "+f"(d[57]), "+f"(d[58]), "+f"(d[59]), "+f"(d[60]), "+f"(d[61]), "+f"(d[62]), "+f"(d[63])
               : "r"(da), "l"(descB), "r"(keep));
}
__device__ __forceinline__ uint64_t make_desc(uint32_t addr, uint32_t lbo_bytes, uint32_t sbo_bytes) {
  return (uint64_t)((addr & 0x3FFFF) >> 4) | ((uint64_t)(lbo_bytes >> 4) << 16) | ((uint64_t)(sbo_bytes >> 4) << 32) | (1ull << 62);
}

__device__ __forceinline__ void ldsm_x4(uint32_t addr, uint32_t& r0, uint32_t& r1, uint32_t& r2, uint32_t& r3) {
  asm volatile("ldmatrix.sync.aligned.m8n8.x4.shared.b16 {%0,%1,%2,%3}, [%4];" : "=r"(r0), "=r"(r1), "=r"(r2), "=r"(r3) : "r"(addr) : "memory");
}
__device__ __forceinline__ void ldsm_x4_t(uint32_t addr, uint32_t& r0, uint32_t& r1, uint32_t& r2, uint32_t& r3) {
  asm volatile("ldmatrix.sync.aligned.m8n8.x4.trans.shared.b16 {%0,%1,%2,%3}, [%4];" : "=r"(r0), "=r"(r1), "=r"(r2), "=r"(r3) : "r"(addr) : "memory");
}
__device__ __forceinline__ void stsm_x4(uint32_t addr, uint32_t r0, uint32_t r1, uint32_t r2, uint32_t r3) {
  asm volatile("stmatrix.sync.aligned.m8n8.x4.shared.b16 [%0], {%1,%2,%3,%4};" :: "r"(addr), "r"(r0), "r"(r1), "r"(r2), "r"(r3) : "memory");
}
__device__ __forceinline__ void sts128(uint32_t addr, uint32_t a, uint32_t b, uint32_t c, uint32_t d) {
  asm volatile("st.shared.v4.u32 [%0], {%1,%2,%3,%4};" :: "r"(addr), "r"(a), "r"(b), "r"(c), "r"(d) : "memory");
}
__device__ __forceinline__ float lds32f(uint32_t addr) {
  float v;
  asm volatile("ld.shared.f32 %0, [%1];" : "=f"(v) : "r"(addr) : "memory");
  return v;
}
__device__ __forceinline__ void sts32f(uint32_t addr, float a) {
  asm volatile("st.shared.f32 [%0], %1;" :: "r"(addr), "f"(a) : "memory");
}
__device__ __forceinline__ void mma_bf16(float (&c)[4], uint32_t a0, uint32_t a1, uint32_t a2, uint32_t a3, uint32_t b0, uint32_t b1) {
  asm volatile("mma.sync.aligned.m16n8k16.row.col.f32.bf16.bf16.f32 {%0,%1,%2,%3}, {%4,%5,%6,%7}, {%8,%9}, {%0,%1,%2,%3};"
               : "+f"(c[0]), "+f"(c[1]), "+f"(c[2]), "+f"(c[3]) : "r"(a0), "r"(a1), "r"(a2), "r"(a3), "r"(b0), "r"(b1));
}
__device__ __forceinline__ void mma_bf16_z(float (&c)[4], uint32_t a0, uint32_t a1, uint32_t a2, uint32_t a3, uint32_t b0, uint32_t b1) {
  asm volatile("mma.sync.aligned.m16n8k16.row.col.f32.bf16.bf16.f32 {%0,%1,%2,%3}, {%4,%5,%6,%7}, {%8,%9}, {%10,%10,%10,%10};"
               : "=f"(c[0]), "=f"(c[1]), "=f"(c[2]), "=f"(c[3]) : "r"(a0), "r"(a1), "r"(a2), "r"(a3), "r"(b0), "r"(b1), "f"(0.f));
}
__device__ __forceinline__ uint32_t movm_t(uint32_t v) {
  uint32_t r;
  asm volatile("movmatrix.sync.aligned.m8n8.trans.b16 %0, %1;" : "=r"(r) : "r"(v));
  return r;
}
__device__ __forceinline__ uint32_t pack_bf16(float lo, float hi) {
  uint32_t r;
  asm("cvt.rn.bf16x2.f32 %0, %1, %2;" : "=r"(r) : "f"(hi), "f"(lo));
  return r;
}
__device__ __forceinline__ float bf_lo(uint32_t v) { return __uint_as_float(v << 16); }
__device__ __forceinline__ float bf_hi(uint32_t v) { return __uint_as_float(v & 0xFFFF0000u); }
__device__ __forceinline__ void split3(float x, uint32_t& h, uint32_t& m, uint32_t& l) {
  h = pack_bf16(x, 0.f); x -= bf_lo(h);
  m = pack_bf16(x, 0.f); x -= bf_lo(m);
  l = pack_bf16(x, 0.f);
}
__device__ __forceinline__ float ex2(float x) { float r; asm("ex2.approx.ftz.f32 %0, %1;" : "=f"(r) : "f"(x)); return r; }
__device__ __forceinline__ float rcp_fast(float x) { float r; asm("rcp.approx.ftz.f32 %0, %1;" : "=f"(r) : "f"(x)); return r; }
__device__ __forceinline__ void red_v4(float* p, float a, float b, float c, float d) {
  asm volatile("red.global.add.v4.f32 [%0], {%1, %2, %3, %4};" :: "l"(p), "f"(a), "f"(b), "f"(c), "f"(d) : "memory");
}
__device__ __forceinline__ uint4 ld_ll(const uint4* p) {
  uint4 v;
  asm volatile("{\n.reg .b64 a, b;\nld.relaxed.gpu.global.v2.b64 {a, b}, [%4];\nmov.b64 {%0, %1}, a;\nmov.b64 {%2, %3}, b;\n}\n"
               : "=r"(v.x), "=r"(v.y), "=r"(v.z), "=r"(v.w) : "l"(p) : "memory");
  return v;
}
__device__ __forceinline__ void st_b64(uint2* p, uint32_t a, uint32_t b) {
  asm volatile("{\n.reg .b64 v;\nmov.b64 v, {%1, %2};\nst.relaxed.gpu.global.b64 [%0], v;\n}\n" :: "l"(p), "r"(a), "r"(b) : "memory");
}
__device__ __forceinline__ void st_b128(uint4* p, uint32_t a, uint32_t b, uint32_t c, uint32_t d) {
  asm volatile("{\n.reg .b128 v;\nmov.b128 v, {%1, %2, %3, %4};\nst.relaxed.gpu.global.b128 [%0], v;\n}\n" :: "l"(p), "r"(a), "r"(b), "r"(c), "r"(d) : "memory");
}
__device__ __forceinline__ uint4 ld_b128(const uint4* p) {
  uint4 v;
  asm volatile("{\n.reg .b128 v;\nld.relaxed.gpu.global.b128 v, [%4];\nmov.b128 {%0, %1, %2, %3}, v;\n}\n" : "=r"(v.x), "=r"(v.y), "=r"(v.z), "=r"(v.w) : "l"(p) : "memory");
  return v;
}

constexpr float LOG2E = 1.4426950408889634f;

struct Params {
  const __nv_bfloat16* x0;
  const __nv_bfloat16* wA_qkv;
  const __nv_bfloat16* wA_o;
  const __nv_bfloat16* wB_qkv;
  const __nv_bfloat16* wB_phi;
  const __nv_bfloat16* wB_o;
  __nv_bfloat16* out;
};

#define ACC_DEF(d, n) _Pragma("unroll") for (int i_ = 0; i_ < (n); i_++) asm volatile("" : "=f"(d[i_]))
#define ACC_FENCE(d, n) _Pragma("unroll") for (int i_ = 0; i_ < (n); i_++) asm volatile("" : "+f"(d[i_]) :: "memory")
#define PIN(a, n) _Pragma("unroll") for (int i_ = 0; i_ < (n); i_++) asm volatile("" : "+f"((a)[i_]))
#define PINU(a, n) _Pragma("unroll") for (int i_ = 0; i_ < (n); i_++) asm volatile("" : "+r"((a)[i_]))

#define V_ADDR(p0) uint32_t va_[2] = {(p0) + (srowoff >> 1) + (lhi ^ lsw2), (p0) + (srowoff >> 1) + ((32 + lhi) ^ lsw2)}
#define STAGE_V(acc) { \
    _Pragma("unroll") for (int j_ = 0; j_ < 4; j_++) { \
      const float* a_ = (acc) + j_ * 8; \
      stsm_x4(va_[j_ & 1] + (j_ >> 1) * 8192, \
              pack_bf16(rs0 * a_[0], rs0 * a_[1]), pack_bf16(rs1 * a_[2], rs1 * a_[3]), pack_bf16(rs0 * a_[4], rs0 * a_[5]), pack_bf16(rs1 * a_[6], rs1 * a_[7])); } }
#define FRAG(dst, acc, TR, grp) { \
    _Pragma("unroll") for (int i_ = 0; i_ < 16; i_++) { \
      const float r_ = (i_ & 1) ? rs1 : rs0; \
      const uint32_t w_ = pack_bf16(r_ * (acc)[2 * i_], r_ * (acc)[2 * i_ + 1]); \
      if (TR) (dst)[i_] = movm_t(w_); else (dst)[(i_ & 12) + (i_ & 1) * 2 + ((i_ >> 1) & 1)] = w_; } \
    if (warp == 7 && mm < 15) { \
      _Pragma("unroll") for (int j_ = 0; j_ < 4; j_++) \
        st_b128(g_halo + (size_t)(mm * 8 + jj) * 512 + ((grp) * 4 + j_) * 32 + lane, ((dst)[j_ * 4] & ~1u) | H_BIT(l), (dst)[j_ * 4 + 1], (dst)[j_ * 4 + 2], (dst)[j_ * 4 + 3]); } \
    PINU(dst, 16); }
#define FRAG_PUT(src, slot) if (warp < 7) { _Pragma("unroll") for (int j_ = 0; j_ < 4; j_++) \
      sts128(sbase + (slot) * SLOT + 2048 + warp * 2048 + j_ * 512 + lane * 16, (src)[j_ * 4], (src)[j_ * 4 + 1], (src)[j_ * 4 + 2], (src)[j_ * 4 + 3]); }
#define FRAG_GET(dst, slot) { _Pragma("unroll") for (int j_ = 0; j_ < 4; j_++) \
      asm volatile("ld.shared.v4.u32 {%0, %1, %2, %3}, [%4];" : "=r"((dst)[j_ * 4]), "=r"((dst)[j_ * 4 + 1]), "=r"((dst)[j_ * 4 + 2]), "=r"((dst)[j_ * 4 + 3]) \
                   : "r"(sbase + (slot) * SLOT + warp * 2048 + j_ * 512 + lane * 16) : "memory"); }
#define RW(j) (((j) >> 1) * 4 + ((j) & 1))
template <int POS> __device__ __forceinline__ float exps16_(float* o, const float* p) {
  float s[4];
#pragma unroll
  for (int j = 0; j < 16; j++) { o[j] = ex2(POS ? p[RW(j)] : -p[RW(j)]); if (j < 4) s[j] = o[j]; else s[j & 3] += o[j]; }
  const float r = (s[0] + s[1]) + (s[2] + s[3]);
  return r + __shfl_xor_sync(0xffffffffu, r, 1);
}
template <int POS> __device__ __forceinline__ void exps16_fix(float* o, const float* p, float& sum) {
  if (__builtin_expect(__any_sync(0xffffffffu, !(sum > SUMLO && sum < SUMHI)), 0)) {
    float m = p[0], q[32];
#pragma unroll
    for (int j = 1; j < 16; j++) m = POS ? fmaxf(m, p[RW(j)]) : fminf(m, p[RW(j)]);
    const float x = __shfl_xor_sync(0xffffffffu, m, 1);
    m = POS ? fmaxf(m, x) : fminf(m, x);
#pragma unroll
    for (int j = 0; j < 16; j++) q[RW(j)] = p[RW(j)] - m;
    sum = exps16_<POS>(o, q);
  }
}
__device__ __forceinline__ void store16(const float* e, float sum, uint32_t dst, uint32_t dsw, int c0) {
  const float inv = rcp_fast(sum);
#pragma unroll
  for (int j = 0; j < 2; j++)
    sts128(dst + (((c0 + j) << 4) ^ dsw), pack_bf16(e[j * 8] * inv, e[j * 8 + 1] * inv), pack_bf16(e[j * 8 + 2] * inv, e[j * 8 + 3] * inv),
           pack_bf16(e[j * 8 + 4] * inv, e[j * 8 + 5] * inv), pack_bf16(e[j * 8 + 6] * inv, e[j * 8 + 7] * inv));
}
template <int POS> __device__ __forceinline__ void expp16(uint32_t* o, float* p) {
  {
#pragma unroll
    for (int r = 0; r < 4; r += 2) {
      float m = p[r];
#pragma unroll
      for (int j = 1; j < 8; j++) m = POS ? fmaxf(m, p[r + RW(j)]) : fminf(m, p[r + RW(j)]);
#pragma unroll
      for (int s = 1; s <= 2; s <<= 1) { const float x = __shfl_xor_sync(0xffffffffu, m, s); m = POS ? fmaxf(m, x) : fminf(m, x); }
#pragma unroll
      for (int j = 0; j < 8; j++) p[r + RW(j)] -= m;
    }
  }
#pragma unroll
  for (int j = 0; j < 8; j++) o[j] = pack_bf16(ex2(POS ? p[2 * j] : -p[2 * j]), ex2(POS ? p[2 * j + 1] : -p[2 * j + 1]));
}
__device__ __forceinline__ void scale32(float* o, const float* p, float c0, float c1) {
#pragma unroll
  for (int i = 0; i < 32; i++) asm volatile("mul.f32 %0, %1, %2;" : "=f"(o[i]) : "f"(p[i]), "f"((i & 2) ? c1 : c0));
}
__device__ __forceinline__ bool any_big(const float* p) {
  float m[4];
#pragma unroll
  for (int i = 0; i < 32; i++) m[i >> 3] = (i & 7) ? fmaf(p[i], p[i], m[i >> 3]) : p[i] * p[i];
  return __any_sync(0xffffffffu, !(fmaxf(fmaxf(m[0], m[1]), fmaxf(m[2], m[3])) < BIGLIM));
}
__device__ __forceinline__ void phiq_a(float* p, bool big) {
  if (__builtin_expect(!big, 1)) {
#pragma unroll
    for (int j = 0; j < 16; j++) p[j] = ex2(p[j]);
  }
}
template <int NEXT> __device__ __forceinline__ void phiq_b(uint32_t* o, float* p, bool big) {
  if (__builtin_expect(big, 0)) {
    expp16<0>(o, p); expp16<1>(o + 8, p);
  } else {
    if (NEXT) phiq_a(p + 16, false);
#pragma unroll
    for (int j = 0; j < 4; j++) {
      const float a = p[4 * j], b = p[4 * j + 1], c = p[4 * j + 2], d = p[4 * j + 3];
      const float ab = a * b, cd = c * d, r = rcp_fast(ab * cd), x = r * cd, y = r * ab;
      o[2 * j] = pack_bf16(x * b, x * a); o[2 * j + 1] = pack_bf16(y * d, y * c);
      o[8 + 2 * j] = pack_bf16(a, b); o[9 + 2 * j] = pack_bf16(c, d);
    }
  }
}
#define SCHED_FENCE() asm volatile("pmevent 0;" ::: "memory")

__global__ void __cluster_dims__(2, 1, 1) __launch_bounds__(384, 1)
mega_kernel(const __grid_constant__ CUtensorMap tm_x0, const __grid_constant__ CUtensorMap tm_xo, const __grid_constant__ CUtensorMap tm_os,
            const __grid_constant__ CUtensorMap tm_o, const __grid_constant__ CUtensorMap tm_wf,
            const __grid_constant__ CUtensorMap tm_wqA, const __grid_constant__ CUtensorMap tm_wqB,
            const __grid_constant__ CUtensorMap tm_woA, const __grid_constant__ CUtensorMap tm_woB,
            const __grid_constant__ CUtensorMap tm_phi, const Params prm) {
  extern __shared__ __align__(1024) uint8_t smem_raw[];
  const uint32_t sbase = smem_u32(smem_raw);
  const uint32_t bar_full = sbase + OFF_BAR;
  const uint32_t bar_done = bar_full + 384;
  const uint32_t bar_stat = bar_full + 768, bar_stat2 = bar_full + 776, bar_epi = bar_full + 784, bar_phi = bar_full + 936  , bar_halo = bar_full + 904  ;
  const uint32_t bar_xr = bar_full + 800, bar_lx = bar_full + 808, bar_stg = bar_full + 832;
  const uint32_t bar_chk = bar_full + 848;

  const int warp = __shfl_sync(0xffffffffu, threadIdx.x >> 5, 0), lane = threadIdx.x & 31;
  uint32_t rank;
  asm volatile("mov.u32 %0, %%cluster_ctarank;" : "=r"(rank));
  const int aux = (int)blockIdx.x - NMAIN, tp = (int)(blockIdx.x >> 1) - 4;
  const int gp = tp < 0 ? 0 : (tp < 32 ? tp & 7 : 1 + (tp - 32) % 7), me = tp < 0 ? tp + 8 : (tp < 32 ? tp >> 3 : 4 + (tp - 32) / 7);
  const int jj = me, cc = gp;
  const int cta = aux >= 0 ? -1 : (cc * 8 + jj) * 2 + (int)rank;
  const int mm = cc * 2 + (int)rank;

#define LOAD_EPOCH() const unsigned epoch = ld_relaxed(&g_flags.epoch.v), ep1 = epoch + 1; (void)epoch
  int budget = 1 << 22;

  if (cta >= 0) {
    if (warp >= 8 && warp < 8 + EARLY && elect_one()) {
      const int u = warp - 8;
      const uint32_t fb = bar_full + u * 8;
      mbar_init(fb, 1);
      asm volatile("fence.mbarrier_init.release.cluster;" ::: "memory");
      fence_proxy_async_smem();
      mbar_expect_tx(fb, u < 2 ? QST + SLOT : QST);
      if (u && STAG2) __nanosleep(STAG2);
      if (u < 2) tma_load_2d(sbase + OFF_S + u * SLOT, &tm_x0, fb, jj * 128 + u * 64, mm * 128);
#pragma unroll
      for (int i = 0; i < 6; i++) tma_load_2d(sbase + u * QST + i * 4096, &tm_wqA, fb, jj * 128 + (u >> 1) * 64 + (i >> 1) * 1024, jj * 128 + (u & 1) * 64 + (i & 1) * 32);
      if (u == 0) PROFT(472);
    }
    __syncwarp();
    {
      const int tx = threadIdx.x;
      const __nv_bfloat16* pf = (tx < 128) ? prm.x0 + (size_t)(mm * 128 + tx) * D_MODEL + jj * 128
                                           : prm.wA_qkv + (size_t)(jj * 128 + (tx & 63)) * 3072 + ((tx - 128) >> 6) * 1024 + jj * 128 + rank * 64;
      if (tx < 320) { if (PF0) asm volatile("prefetch.global.L2 [%0];" :: "l"(pf)); }
      else if (tx == 320) prefetch_tmap(&tm_x0);
      else if (tx == 352) prefetch_tmap(&tm_wqA);
      else if (tx == 383) asm volatile("prefetch.global.L2 [%0];" :: "l"(&g_flags.epoch.v));
    }
    if (elect_one()) {
#pragma unroll
      for (int i = 0; i < 4; i++) {
        const int u = warp * 4 + i;
        if (u >= EARLY) mbar_init(bar_full + u * 8, ((u >= 4 && u < 11) || (u > 32 && u != 40)) ? 2 : 1); mbar_init(bar_done + u * 8, 16);
      }
      mbar_init(bar_stat + warp * 16, 0x111111181182ull >> (4 * warp) & 15);
      mbar_init(bar_stat + warp * 16 + 8, 0x111111121811ull >> (4 * warp) & 15);
      mbar_init(bar_chk + 112 + (warp & 7) * 8, 1);
      asm volatile("fence.mbarrier_init.release.cluster;" ::: "memory");
    }
    __syncthreads();
    asm volatile("barrier.cluster.arrive.relaxed.aligned;" ::: "memory");
  }

  if (cta < 0) {
    LOAD_EPOCH();
    const uint32_t buf = sbase + warp * SLOT, bar = sbase + OFF_BAR + warp * 16;
    const uint32_t lsw = (lane & 7) << 4, lhi = (lane >> 4) << 4, lrow = (lane & 15) * 128;
    const bool el = elect_one();
    if (el) {
      mbar_init(bar, 1); mbar_init(bar + 8, 1);
      asm volatile("fence.mbarrier_init.release.cluster;" ::: "memory");
    }
#pragma unroll 1
    for (int rd = 0; rd < (NLAYERS > 1 ? 5 : 2); rd++) {
      if (rd >= 2 && warp >= 8) break;
      const int tk = rd < 2 ? aux * 12 + warp : aux * 8 + warp;
      const int half = tk & 1;
      const int blk = rd < 2 ? (tk >> 1) * 2 + rd : (4 - rd) * 16 + (tk >> 1);
      const CUtensorMap* tm = rd < 2 ? &tm_wqA : (rd == 2 ? &tm_wqB : &tm_wf);
      const int j0 = (blk & 15) >> 1;
#define AUX_LOAD(n) { const uint32_t d_ = buf + ((n) & 1) * 8192, b_ = bar + ((n) & 1) * 8; const int r_ = kslice(j0, 2 * (n) + half) * 64; \
        mbar_expect_tx(b_, 8192); tma_load_2d(d_, tm, b_, blk * 64, r_); tma_load_2d(d_ + 4096, tm, b_, blk * 64, r_ + 32); }
      if (el) {
        if (rd == 3) { wait_flag(&g_flags.wfready[j0].v, ep1 * 16); fence_proxy_async_global(); }
        AUX_LOAD(0); AUX_LOAD(1);
      }
      __syncwarp();
      float cs[8][4];
#pragma unroll
      for (int i = 0; i < 8; i++) cs[i][0] = cs[i][1] = cs[i][2] = cs[i][3] = 0.f;
#pragma unroll 1
      for (int n = 0; n < 8; n++) {
        const uint32_t tb = buf + (n & 1) * 8192 + lrow;
        mbar_wait(bar + (n & 1) * 8, (n >> 1) & 1);
#pragma unroll
        for (int i = 0; i < 16; i++) {
          uint32_t b0, b1, b2, b3;
          ldsm_x4_t(tb + (i >> 2) * 2048 + (((i & 3) * 32 + lhi) ^ lsw), b0, b1, b2, b3);
          mma_bf16(cs[2 * (i & 3)], 0x3F803F80u, 0x3F803F80u, 0x3F803F80u, 0x3F803F80u, b0, b1);
          mma_bf16(cs[2 * (i & 3) + 1], 0x3F803F80u, 0x3F803F80u, 0x3F803F80u, 0x3F803F80u, b2, b3);
        }
        __syncwarp();
        if (el && n < 6) AUX_LOAD(n + 2);
        __syncwarp();
      }
      if (lane < 4) {
#pragma unroll
        for (int i = 0; i < 8; i++) st_b64(&g_colsum[rd >= 2][blk * 32 + i * 4 + lane][half], __float_as_uint(cs[i][0]), (__float_as_uint(cs[i][1]) & ~3u) | (ep1 & 3));
      }
      __syncwarp();
    }
  } else if (warp >= 8) {
    asm volatile("setmaxnreg.dec.sync.aligned.u32 40;");
    if (warp == 8) {
      const bool el = elect_one();
      cluster_wait();
      if (el) {
#pragma unroll 1
        for (int l = 0; l < NLAYERS; l++) {
          const uint32_t par = l & 1;
          const CUtensorMap* tqk = par ? &tm_wf : &tm_wqA;
          const CUtensorMap* tv = par ? &tm_wqB : &tm_wqA;
          const CUtensorMap* two = par ? &tm_woB : &tm_woA;
          if (l == 1) { LOAD_EPOCH(); wait_flag(&g_flags.wfready[jj].v, ep1 * 16); fence_proxy_async_global(); }
#pragma unroll 1
          for (int u = l ? 0 : EARLY; u < 32; u++) {
            if (u >= 4) mbar_wait_sl(bar_done + (u - 4) * 8, par);
            else if (l) mbar_wait_sl(bar_done + (43 + u + (u >> 1)) * 8, par ^ 1);
            else if (u == 1) __nanosleep(STAG1);
            else if (u == 2 && !W23) mbar_wait_sl(bar_full, 0);
            const uint32_t fb = bar_full + u * 8;
            const bool res = u < 4 ? (l || u >= 2) : (u < 11 || (u >= 18 && u < 22));
            mbar_expect_tx(fb, res ? QST : QST + SLOT);
            const int row = kslice(jj, u < 4 ? u & 1 : (u < 18 ? u - 2 : (u < 22 ? u - 6 : u - 20))) * 64 + (int)rank * 32;
            const int ps = u < 4 ? u >> 1 : (u >= 18), col = jj * 128 + ps * 64;
            const int c0 = par ? jj * 128 + (ps ? 0 : 1024) : col;
            const uint32_t dst = sbase + (u & 3) * QST + rank * 4096;
            tma_load_2d_mc(dst, tqk, fb, c0, row);
            tma_load_2d_mc(dst + 8192, tqk, fb, c0 + (par ? 64 : 1024), row);
            tma_load_2d_mc(dst + 16384, tv, fb, col + 2048, row);
            if (l == PRL && u >= PRU && u < PRU + 4) PROFT(473 + u - PRU);
          }
#pragma unroll 1
          for (int s = 0; s < 16; s++) {
            if (s < 5) { if (s != 2 && s != 4) mbar_wait_sl(bar_done + (28 + s) * 8, par); }
            else if (s != 14) mbar_wait_sl(bar_done + (27 + s - (s == 15)) * 8, par);
            const uint32_t fb = bar_full + (32 + s) * 8;
            mbar_expect_tx(fb, SLOT);
            tma_load_2d_mc(sbase + rank * 8192 + (uint32_t)((WO_BSLOT >> (4 * s)) & 15) * SLOT, two, fb, jj * 128 + (int)rank * 64, wslice(jj, s) * 64);
            const int ts = s + par;
            if (s >= 5 && ts < 8) {
              mbar_expect_tx(bar_chk - 8 + ts * 8, SLOT);
              tma_load_2d(sbase + (uint32_t)((WO_ASLOT(par) >> (4 * ts)) & 15) * SLOT, &tm_o, bar_chk - 8 + ts * 8, wslice(jj, ts) * 64, mm * 128);
            }
          }
        }
      }
      __syncwarp();
    } else if (warp == 9) {
      const bool el = elect_one();
      if (el) {
        if (!EARLY) { PROFT(472); tma_load_2d(sbase + OFF_S, &tm_x0, bar_full, jj * 128, mm * 128); }
        if (EARLY < 2) { __nanosleep(STAG1); tma_load_2d(sbase + OFF_S + SLOT, &tm_x0, bar_full + 8, jj * 128 + 64, mm * 128); }
      }
      __syncwarp();
      LOAD_EPOCH();
#pragma unroll 1
      for (int lp = 0; lp < 4 * NLAYERS; lp++) {
        const int l = lp >> 2, ph = lp & 3;
        if (ph == 3) continue;
        const uint32_t par = l & 1;
        const unsigned* pp = reinterpret_cast<const unsigned*>(g_obuf + (ph >> 1) * 64 + (size_t)(mm * 128 + (ph ? 0 : S_LEN) + (lane & 7) * 16 + (jj & 1) * 8) * D_MODEL +
                                                               (jj >> 1) * 16 + srcb(jj, lane >> 3) * 128);
        const CUtensorMap* tm = lp ? &tm_o : &tm_x0;
        const int row = mm * 128 + ((ph || !l) ? 0 : S_LEN);
        const uint32_t bit = ph ? O_BIT(l) : X_BIT(l - 1);
        const uint32_t slots = ph ? (uint32_t)(WO_ASLOT(par) >> (ph * 32 - 28)) : 0x8769876u;
        const unsigned long long fr = ph == 0 ? XPACE : ph == 1 ? (par ? 0x353535351Full : 0x35351F1Eull) : (par ? 0x27262524232232ull : 0x27262524233232ull);
        uint32_t no = (lp == 0 || (lp & 7) == 1) ? 0 : ~0u, v0 = 0, v1 = 0;
        if (lp || !AX) mbar_wait_sl(ph ? bar_done + ((uint32_t)fr & 63) * 8 : (l ? bar_done + 47 * 8 : bar_full), ph ? par : (l ? par ^ 1 : 0));
        if (el && ph) PROFT(324 + l * 16 + ph);
        __syncwarp();
        if (no) { v0 = ld_relaxed(pp); __nanosleep(POLLGAP); v1 = ld_relaxed(pp); }
#pragma unroll 1
        for (int i = 0; i < (ph == 1 ? 4 + par : 7); i++, no >>= 8) {
#pragma unroll 1
          for (int it = 0; (no & 0xFF) && it < (1 << 18); it++) {
            no &= __ballot_sync(0xffffffffu, (v0 ^ bit) & 1) >> (8 * i);
            if (no) v0 = ld_relaxed(pp);
            if (!(no & 0xFF)) break;
            no &= __ballot_sync(0xffffffffu, (v1 ^ bit) & 1) >> (8 * i);
            if (no) v1 = ld_relaxed(pp);
          }
          if (ph || i >= XP0) mbar_wait_sl(bar_done + ((uint32_t)(fr >> (8 * i)) & 63) * 8, par);
          if (el) {
            if (i == 0) PROFT(320 + l * 16 + ph);
            const uint32_t cb = bar_chk + (ph >> 1) * 112 + i * 8;
            mbar_expect_tx(cb, SLOT);
            tma_load_2d(sbase + ((slots >> (4 * i)) & 15) * SLOT, tm, cb, srcb(jj, i) * 128 + (ph >> 1) * 64, row);
          }
          __syncwarp();
        }
        if (ph == 0 && el) {
          if (l) { wait_flag(&g_flags.xready[l][mm].v, ep1 * 8); fence_proxy_async_global(); }
#pragma unroll 1
          for (int u = 11; u < 34; u++) {
            if (u == 18) u = 22;
            mbar_wait_sl(bar_done + (u - 4) * 8, par);
            if (u == 32) mbar_expect_tx(bar_xr, 2 * SLOT);
            tma_load_2d(sbase + OFF_RA + (u & 3) * SLOT, tm, u < 32 ? bar_full + u * 8 : bar_xr, kslice(jj, u < 18 ? u - 2 : (u < 32 ? u - 20 : u - 32)) * 64, row);
          }
        }
        __syncwarp();
      }
      if (el && atomicAdd(&g_flags.done.v, 1) == ep1 * NMAIN - 1) asm volatile("st.relaxed.gpu.global.u32 [%0], %1;" :: "l"(&g_flags.epoch.v), "r"(ep1) : "memory");
      __syncwarp();
      cluster_wait();
    } else {
      const int hw = warp - 10;
      LOAD_EPOCH();
      const bool el = elect_one();
      cluster_wait();
      if (hw == 0) {
        mbar_wait_sl(bar_full + 8, 0);
        if (lane < 7) prefetch_tmap(lane == 0 ? &tm_os : lane == 1 ? &tm_o : lane == 2 ? &tm_wf : lane == 3 ? &tm_wqB : lane == 4 ? &tm_woA : lane == 5 ? &tm_woB : &tm_phi);
#pragma unroll 1
        for (int i = 0; i < (NLAYERS > 1 ? 9 : 0); i++) {
          if (i == 0 || i == 5) mbar_wait_sl(bar_done + (i >> 1) * 12, 0);
          if (el) {
            if (i == 0) { mbar_expect_tx(bar_phi, 2 * SLOT + 8192); tma_load_2d(sbase + OFF_PHI, &tm_phi, bar_phi, 0, jj * 128); }
            else tma_load_2d(sbase + (i > 4 ? 10 : 12) * SLOT - 4096 + i * 4096, &tm_wqB, bar_phi, (i > 4 ? 896 : 0) + jj * 128 + ((i - 1) >> 1) * 64, mm * 64 + (~i & 1) * 32);
          }
          __syncwarp();
          __nanosleep(PFGAP);
        }
      } else {
        if (XMMA && lane < 24) {
          const uint32_t one = (lane & 8) ? 0u : 0x3F80u << ((lane & 1) * 16), w = (lane >> 1) & 3;
          sts128(sbase + OFF_ID + lane * 16, w == 0 ? one : 0u, w == 1 ? one : 0u, w == 2 ? one : 0u, w == 3 ? one : 0u);
        }
#pragma unroll 1
        for (int b = 0; b < 2; b++) {
          float4* z = reinterpret_cast<float4*>(g_kv[b] + (jj * 4) * KVH + mm * (4 * KVH / 16)) + lane;
#pragma unroll
          for (int i = 0; i < 6; i++) z[i * 32] = make_float4(0.f, 0.f, 0.f, 0.f);
        }
#pragma unroll 1
        for (int i = 0; i < 16; i++) {
          const int b = i >> 2;
          const uint32_t v = (b == 0 ? O_BIT(0) : b == 1 ? X_BIT(0) : H_BIT(0)) + 1;
          uint4* p = b < 2 ? reinterpret_cast<uint4*>(g_obuf + (size_t)(b * S_LEN + mm * 128 + (i & 3) * 32 + (lane >> 3) * 8) * D_MODEL + jj * 128 + (b ? 0 : 64)) + (lane & 7)
                           : g_halo + (size_t)(mm * 8 + jj) * 512 + i * 32 + lane;
          *p = make_uint4(v, v, v, v);
        }
        fence_proxy_async_global();
      }
      __syncwarp();
      uint32_t chkp = 0;
#pragma unroll 1
      for (int lp = 0; lp < 8 * NLAYERS; lp++) {
        const int l = lp >> 3, tk = lp & 7, ph = tk ? 2 - hw : 0;
        const uint32_t par = l & 1;
        int lane; asm volatile("mov.u32 %0, %%laneid;" : "=r"(lane));
        if (tk == 5 || (hw && tk == 0)) {
          const uint32_t bit = ph ? O_BIT(l) : X_BIT(l - 1);
          uint32_t slots = ph ? (uint32_t)(WO_ASLOT(par) >> (ph * 32 - 28)) : 0x8769876u;
          const uint32_t a0 = sbase + (lane & 7) * 132 + (lane >> 3) * 32;
#pragma unroll 1
          for (int c = 0; c < 7; c++, slots >>= 4) {
            const uint32_t cb = bar_chk + 112 - hw * 112 + c * 8;
#pragma unroll 1
            for (int it = 0; it < (1 << 12); it++) {
              mbar_wait_sl(cb, (chkp >> c) & 1);
              chkp ^= 1u << c;
              if (el && c == 0) PROFT(ph == 1 ? 480 + l * 2 : 488 + l * 2 + (ph >> 1));
              if (lp == 0) break;
              uint32_t bad;
              asm volatile("{\n.reg .b32 w<16>;\n"
                           "ld.shared.u32 w0, [%1 + 0];\n"
                           "ld.shared.u32 w1, [%1 + 1024];\n"
                           "ld.shared.u32 w2, [%1 + 2048];\n"
                           "ld.shared.u32 w3, [%1 + 3072];\n"
                           "ld.shared.u32 w4, [%1 + 4096];\n"
                           "ld.shared.u32 w5, [%1 + 5120];\n"
                           "ld.shared.u32 w6, [%1 + 6144];\n"
                           "ld.shared.u32 w7, [%1 + 7168];\n"
                           "ld.shared.u32 w8, [%1 + 8192];\n"
                           "ld.shared.u32 w9, [%1 + 9216];\n"
                           "ld.shared.u32 w10, [%1 + 10240];\n"
                           "ld.shared.u32 w11, [%1 + 11264];\n"
                           "ld.shared.u32 w12, [%1 + 12288];\n"
                           "ld.shared.u32 w13, [%1 + 13312];\n"
                           "ld.shared.u32 w14, [%1 + 14336];\n"
                           "ld.shared.u32 w15, [%1 + 15360];\n"
                           "lop3.b32 w0, w0, w1, %2, 0x7E;\n"
                           "lop3.b32 w2, w2, w3, %2, 0x7E;\n"
                           "lop3.b32 w4, w4, w5, %2, 0x7E;\n"
                           "lop3.b32 w6, w6, w7, %2, 0x7E;\n"
                           "lop3.b32 w8, w8, w9, %2, 0x7E;\n"
                           "lop3.b32 w10, w10, w11, %2, 0x7E;\n"
                           "lop3.b32 w12, w12, w13, %2, 0x7E;\n"
                           "lop3.b32 w14, w14, w15, %2, 0x7E;\n"
                           "lop3.b32 w0, w0, w2, w4, 0xFE;\nlop3.b32 w6, w6, w8, w10, 0xFE;\nlop3.b32 w0, w0, w12, w14, 0xFE;\nlop3.b32 %0, w0, w6, 1, 0xA8;\n}\n"
                           : "=r"(bad) : "r"(a0 + (slots & 15) * SLOT), "r"(bit) : "memory");
              if (__all_sync(0xffffffffu, bad == 0)) break;
              if (el) {
                fence_proxy_async_smem();
                mbar_expect_tx(cb, SLOT);
                tma_load_2d(sbase + (slots & 15) * SLOT, &tm_o, cb, srcb(jj, c) * 128 + (ph >> 1) * 64, mm * 128 + (ph ? 0 : S_LEN));
                RETRY_COUNT();
              }
              __syncwarp();
            }
            if (el) { mbar_arrive_local(bar_full + (c + (ph ? 25 + ph * 8 : 4)) * 8); if (lp == PRL * 8 && c == 0) PROFT(477); }
            __syncwarp();
          }
        } else if (hw && (tk & 5) == 1) {
          {
            const int hp = tk >> 1;
            const uint4* src = reinterpret_cast<const uint4*>(g_colsum[par][jj * 64 + hp * 32 + lane]);
            uint32_t bad;
            int it = 0;
            float c[6];
            do {
              bad = 0;
#pragma unroll
              for (int p = 0; p < 3; p++) {
                const uint4 v = ld_ll(src + ((par && p < 2) ? (hp ? -32 : 512) + p * 32 : p * 512));
                bad |= (v.y ^ ep1) | (v.w ^ ep1);
                c[2 * p] = __uint_as_float(v.x) + __uint_as_float(v.z); c[2 * p + 1] = __uint_as_float(v.y) + __uint_as_float(v.w);
              }
              bad &= 3;
              if (bad) __nanosleep(300);
            } while (bad && ++it < (1 << 16));
#pragma unroll
            for (int p = 0; p < 6; p++) {
              uint32_t h, m, lo;
              split3(c[p], h, m, lo);
              sts128(sbase + OFF_LNB + hp * 4096 + (p >> 1) * 1024 + lane * 32 + (p & 1) * 16, h | (m << 16), h | (lo << 16), h | (m << 16), lo | (m << 16));
            }
            fence_proxy_async_smem();
            __syncwarp();
            if (el) { mbar_arrive_local(hp ? bar_stat2 : bar_stat); if (hp == 0) PROFT(324 + l * 16); }
            __syncwarp();
          }
        } else if (tk == 0) {
          mbar_wait_sl(bar_done + 24, par);
          const uint4* sp = reinterpret_cast<const uint4*>(g_stats + (size_t)(mm * 128) * 8) + lane;
#pragma unroll 1
          for (int hf = 0; hf < 4; hf++) {
            uint4 v[4];
            uint32_t bad;
            int it = 0;
            do {
              bad = 0;
#pragma unroll
              for (int i = 0; i < 4; i++) { v[i] = ld_ll(sp + (hf * 4 + i) * 32); bad |= (v[i].y ^ STAT_TAG(l)) | (v[i].w ^ STAT_TAG(l)); }
              bad &= 3;
              if (bad) __nanosleep(200);
            } while (bad && ++it < (1 << 16));
            __syncwarp();
            float mean = 0.f, m2 = 0.f;
#pragma unroll
            for (int i = 0; i < 4; i++) {
              float a = __uint_as_float(v[i].x) + __uint_as_float(v[i].z);
              a += __shfl_xor_sync(0xffffffffu, a, 1); a += __shfl_xor_sync(0xffffffffu, a, 2);
              a *= 0.125f;
              const float e0 = __uint_as_float(v[i].x) - a, e1 = __uint_as_float(v[i].z) - a;
              float q = fmaf(fmaf(e0, e0, e1 * e1), 128.f, __uint_as_float(v[i].y) + __uint_as_float(v[i].w));
              q += __shfl_xor_sync(0xffffffffu, q, 1); q += __shfl_xor_sync(0xffffffffu, q, 2);
              if ((lane & 3) == i) { mean = a; m2 = q; }
            }
            const uint32_t row = hf * 32 + (lane & 3) * 8 + (lane >> 2);
            uint32_t h, m, lo;
            split3(-0.5f * mean, h, m, lo);
            sts128(sbase + OFF_LNA + row * 16, h | (h << 16), m | (h << 16), lo | (m << 16), m | (lo << 16));
            sts32f(sbase + OFF_ST + row * 4, rsqrtf(m2 * (1.f / 1024.f) + 1e-5f));
          }
          fence_proxy_async_smem();
          __syncwarp();
          if (el) { mbar_arrive_local(bar_stat); PROFT(323 + l * 16); }
          __syncwarp();
#pragma unroll 1
          for (int i = 0; i < 8 - 4 * l; i++) {
            asm volatile("prefetch.global.L2 [%0];" :: "l"(i < 4 ? (l ? prm.wB_o : prm.wA_o) + (size_t)cta * 8192 + i * 2048 + lane * 64
                                                                 : prm.wB_qkv + (size_t)(cta * 8 + (i - 4) * 2 + (lane >> 4)) * 3072 + 2048 + (lane & 15) * 64));
            __nanosleep(PFGAP);
          }
        } else if (lp == 3) {
#pragma unroll 1
          for (int c = 0; c < (NLAYERS > 1 ? 8 : 0); c++) {
            if (!(c & 3)) asm volatile("bar.sync %0, 288;" :: "r"(BAR_WF + (c >> 2)) : "memory");
            if (el) {
              tma_store_2d(&tm_wf, sbase + 11 * SLOT + c * 4096, (c < 4 ? 1024 : -128) + jj * 128 + (c >> 1) * 64, mm * 64 + (c & 1) * 32);
              if ((c & 3) == 3) {
                asm volatile("cp.async.bulk.commit_group;\ncp.async.bulk.wait_group.read 0;" ::: "memory");
                mbar_arrive_local(bar_phi + (c >> 2) * 8);
              } else __nanosleep(WFGAP);
            }
            __syncwarp();
          }
          if (el) { bulk_commit_wait(); signal_release(&g_flags.wfready[jj].v); PROFT(335); }
          __syncwarp();
        } else if (tk == 2 || tk == 4) {
          if (par) continue;
          const int i = tk >> 2;
          mbar_wait_sl(bar_done + (i ? HW1 : (hw ? 19 : HW0)) * 8, 0);
          const uint4* src = g_halo + (size_t)(mm * 8 + jj - 8) * 512 + i * 256 + hw * 128 + lane;
          uint4 v[4];
          int it = 0;
          bool ok;
          do {
#pragma unroll
            for (int j = 0; j < 4; j++) v[j] = mm ? ld_b128(src + j * 32) : make_uint4(H_BIT(l), 0, 0, 0);
            ok = __all_sync(0xffffffffu, (((v[0].x ^ H_BIT(l)) | (v[1].x ^ H_BIT(l)) | (v[2].x ^ H_BIT(l)) | (v[3].x ^ H_BIT(l))) & 1) == 0);
          } while (!ok && ++it < (1 << 16));
          if (lp + hw == 3 && NLAYERS > 1) mbar_wait_sl(bar_phi, 1);
#pragma unroll
          for (int j = 0; j < 4; j++) sts128(sbase + OFF_S + hw * SLOT + j * 512 + lane * 16, v[j].x, v[j].y, v[j].z, v[j].w);
          __syncwarp();
          if (el) { mbar_arrive_local(bar_halo + hw * 8); PROFT(331 + l * 16 + i * 2 + hw); }
          __syncwarp();
        } else if (tk == 6 && hw == 0 && l < NLAYERS - 1) {
          bar_sync<BAR_X1, 288>();
          if (el) {
            PROFT(328 + l * 16);
            mbar_wait_sl(bar_full + XD * 8, par ^ 1);
            tma_store_2d(&tm_o, sbase + 11 * SLOT, jj * 128 + 64, mm * 128 + S_LEN);
            bulk_commit_wait();
            signal_release(&g_flags.xready[l + 1][mm].v);
            PROFT(330 + l * 16);
          }
          __syncwarp();
        }
      }
    }
    cluster_sync();
  } else {
    asm volatile("setmaxnreg.inc.sync.aligned.u32 232;");
    LOAD_EPOCH();
    const int wg = warp >> 2;
    const int r0 = warp * 16;
    const uint32_t pK = sbase + OFF_S, pV = sbase + OFF_S + SLOT;
#define PMASKS(on, bit) const uint32_t pm0 = ((on) && t == (g & 3) && (g >> 2) == (g & 1)), pm1 = ((on) && t == (g & 3) && (g >> 2) != (g & 1)), pbit = (bit)
#define PBIT0(w) (((w) & ~pm0) | (pbit & pm0))
#define PBIT1(w) (((w) & ~pm1) | (pbit & pm1))
#define LANE_CONSTS() \
    int lane; asm volatile("mov.u32 %0, %%laneid;" : "=r"(lane)); \
    const int g = lane >> 2, t = lane & 3; \
    const uint32_t srowoff = (r0 + (lane & 15)) * 128, lsw = (lane & 7) << 4, lhi = (lane >> 4) << 4, lsw2 = (lane & 6) << 3; \
    (void)g; (void)t; (void)srowoff; (void)lsw; (void)lhi; (void)lsw2;
    uint32_t stgp = 0, peer;
    asm volatile("mapa.shared::cluster.u32 %0, %1, %2;" : "=r"(peer) : "r"(sbase), "r"(rank ^ 1));
    peer -= sbase;
    const uint32_t dA0 = (((sbase & 0x3FFFF) + wg * 8192) >> 4) | 0x10000u, dB0 = ((sbase & 0x3FFFF) >> 4) | 0x2000000u;
    cluster_wait();
#define DESC(lo, hi) ((uint64_t)(uint32_t)(lo) | ((uint64_t)(hi) << 32))
#define STG_ARRIVE() { __syncwarp(); if (elect_one()) mbar_arrive_local(bar_stg); }
#define STG_WAIT() { mbar_wait(bar_stg, stgp); stgp ^= 1; }
#define PROFS() do {} while (0)
#define REL(addr) { if (elect_one()) { mbar_arrive_local(addr); asm volatile("mbarrier.arrive.shared::cluster.b64 _, [%0];" :: "r"((addr) + peer) : "memory"); } }
#define QSTEP(ACC, DA, SC, PRE) { \
      const uint32_t da = (DA), db = dB0 + (ub & 0x18) * (QST >> 7); \
      mbar_wait(ub, par); \
      PRE; \
      wgmma_fence(); \
      wgmma4_n192<SC>(ACC, da, db); \
      wgmma_commit(); PROFS(); }
#define QREL() { wgmma_wait<1>(); REL(ub + 376); ub += 8; }
#define RA_CUR (dA0 + (OFF_RA >> 4) + (ub & 0x18) * (SLOT >> 7))
#define PUMP1() { QSTEP(S1, RA_CUR, 1, {}); QREL(); }
#define PUMP0() { PUMP1(); SCHED_FENCE(); }
#define PUMP() if (h == 0) PUMP1()
#define WSTEP() WSTEPH({})
#define WSTEPH(HOOK) { \
      const uint32_t s4 = (ub - bar_full - 256) >> 1; \
      const uint32_t da = dA0 + (((uint32_t)(WO_ASLOT(par) >> s4) & 15) << 10), db = dB0 + (((uint32_t)(WO_BSLOT >> s4) & 15) << 10); \
      mbar_wait(ub, par); \
      wgmma_fence(); \
      wgmma4_n128<1>(S1, da, db); \
      wgmma_commit(); PROFS(); \
      HOOK; \
      wgmma_wait<1>(); \
      if (s4) REL(ub + 376); \
      ub += 8; }
#define PUMPS(n) { _Pragma("unroll 1") for (int i_ = 0; i_ < (n); i_++) PUMP1(); }
#define SITE(n) { if ((BMASK >> (n)) & 1) PUMP1(); SCHED_FENCE(); }
#define LNSTEP(ACC, hh) { wgmma_fence(); wgmma_n192<1, 0>(ACC, make_desc(sbase + OFF_LNA + wg * 1024, 0, 128) ^ (1ull << 62), make_desc(sbase + OFF_LNB + (hh) * 4096, 0, 128) ^ (1ull << 62)); }
#define WARP_STORE(tm, tile, col, row) { fence_proxy_async_smem(); __syncwarp(); \
      if (elect_one()) { tma_store_2d(tm, (tile) + r0 * 128, col, (row) + r0); asm volatile("cp.async.bulk.commit_group;" ::: "memory"); } __syncwarp(); }
#define PUBLISH_O() WARP_STORE(&tm_os, pO, jj * 128 + h * 64, mm * 128)
#define TILE_CONSTS(base, on, bit) \
      uint32_t ta[6]; \
      { PMASKS(on, bit); (void)pbit; ta[4] = pm0; ta[5] = pm1; } \
      _Pragma("unroll") for (int j = 0; j < 4; j++) ta[j] = (base) + srowoff + ((((uint32_t)j << 5) + lhi) ^ lsw); \
      PINU(ta, 6); SCHED_FENCE(); \
      const uint32_t pm0 = ta[4], pm1 = ta[5], pbit = (bit)
#define X_OUT(pc) { \
      _Pragma("unroll") for (int j = (pc) * 4; j < (pc) * 4 + 4; j++) \
        stsm_x4(ta[j & 3] + (pc) * SLOT, \
                PBIT0(pack_bf16(S1[j * 8 + 0], S1[j * 8 + 1])), PBIT0(pack_bf16(S1[j * 8 + 2], S1[j * 8 + 3])), \
                PBIT1(pack_bf16(S1[j * 8 + 4], S1[j * 8 + 5])), PBIT1(pack_bf16(S1[j * 8 + 6], S1[j * 8 + 7]))); }
#define REST_P1(SKEW) { \
      mbar_wait(bar_stat2, par); \
      LNSTEP(S1, 1); \
      _Pragma("unroll 1") while (ub < bar_full + 256) { \
        if (ub == bar_full + 256 - 8 * (SKEW) && wg == 0) bar_sync<BAR_SKEW, 256>(); \
        QSTEP(S1, RA_CUR, 1, {}); \
        if (ub == bar_full + 248 && wg == 1) bar_arrive<BAR_SKEW, 256>(); \
        QREL(); \
      } \
      mbar_wait(bar_done + (31 - (SKEW)) * 8, par);        \
      wgmma_wait<0>(); \
      ACC_FENCE(S1, 96); \
      REL(bar_done + 31 * 8); \
      PROF(13); }
#define FOLD(tile, rd) { \
          LANE_CONSTS(); \
          float d[32]; \
          ACC_DEF(d, 32); \
          mbar_wait(bar_phi, 0); \
          wgmma_fence(); \
          _Pragma("unroll") for (int i = 0; i < 2; i++) { \
            const uint64_t da = make_desc((tile) + wg * 8192 + i * 64, 16, 1024); \
            const uint64_t db = make_desc(sbase + OFF_PHI + wg * 4096 + i * 2048, 16, 512) ^ (3ull << 62); \
            wgmma_n32<0>(d + i * 16, da, db); wgmma_n32<1>(d + i * 16, da + 2, db + 64); \
          } \
          wgmma_commit(); \
          PUMP0(); \
          ACC_FENCE(d, 32); \
          bar_wg(wg); \
          _Pragma("unroll") for (int i = 0; i < 4; i++) { \
            const float* x = d + (i & 1) * 8 + (i >> 1) * 2; \
            if (rd) sts128((tile) + wg * 8192 + ((warp & 3) * 16 + (i >> 1) * 8 + g) * 128 + (((2 * t + (i & 1)) ^ g) << 4), \
                           pack_bf16(x[0], x[1]), pack_bf16(x[4], x[5]), pack_bf16(x[16], x[17]), pack_bf16(x[20], x[21])); \
            else stsm_x4((tile) + srowoff + ((((uint32_t)i << 5) + lhi) ^ lsw), pack_bf16(d[i * 8], d[i * 8 + 1]), pack_bf16(d[i * 8 + 2], d[i * 8 + 3]), \
                         pack_bf16(d[i * 8 + 4], d[i * 8 + 5]), pack_bf16(d[i * 8 + 6], d[i * 8 + 7])); \
          } \
          }
#define LOAD_X0(base) \
      _Pragma("unroll") for (int j = 0; j < 8; j++) { \
        uint32_t x0, x1, x2, x3; \
        ldsm_x4((base) + (j >> 2) * SLOT + srowoff + ((((uint32_t)(j & 3) << 5) + lhi) ^ lsw), x0, x1, x2, x3); \
        S1[j * 8 + 0] = bf_lo(x0); S1[j * 8 + 1] = bf_hi(x0); S1[j * 8 + 2] = bf_lo(x1); S1[j * 8 + 3] = bf_hi(x1); \
        S1[j * 8 + 4] = bf_lo(x2); S1[j * 8 + 5] = bf_hi(x2); S1[j * 8 + 6] = bf_lo(x3); S1[j * 8 + 7] = bf_hi(x3); \
      }
#define XM_ISSUE(keep) { mbar_wait(bar_xr, par); wgmma_fence(); \
      wgmma_copy(T_, dA0 + (OFF_RA >> 4), ((keep) ? make_desc(sbase + OFF_ID + 128, 0, 0) : make_desc(sbase + OFF_ID, 128, 128)) ^ (1ull << 62), keep); }
#define COPY64(d, s) _Pragma("unroll") for (int i_ = 0; i_ < 64; i_++) { uint32_t c_; asm volatile("mov.b32 %0, %1;" : "=r"(c_) : "f"(s[i_])); d[i_] = __uint_as_float(c_); }
#define XM_DONE(c) { ACC_FENCE(T_, 64); COPY64(S1, T_); ACC_FENCE(S1, 64); \
      __syncwarp(); if ((c) && elect_one()) mbar_arrive_local(bar_lx); }
#define LOAD_X() { float T_[64]; ACC_DEF(T_, 64); wgmma_wait<0>(); XM_ISSUE(0); wgmma_commit(); wgmma_wait<0>(); XM_DONE(true); }

    float S1[96];
#pragma unroll
    for (int i = 0; i < 64; i++) S1[i] = 0.f;
#pragma unroll 1
    for (int l = 0; l < NLAYERS; l++) {
      const uint32_t par = l & 1;
      bar_wg(wg);
      PROF(0);
      uint32_t ub = bar_full;
      float S0[96];
      {
        LANE_CONSTS();
        ACC_DEF(S0, 96);
        QSTEP(S0, dA0 + (OFF_S >> 4), 0, {});
        ub += 8;
        PROF(1);
        uint32_t ta[4];
#pragma unroll
        for (int j = 0; j < 4; j++) ta[j] = pK + srowoff + ((((uint32_t)j << 5) + lhi) ^ lsw);
        if (l) { PMASKS(false, 0); X_OUT(1); fence_proxy_async_smem(); }
        float p0, p1, a0 = 0.f, a1 = 0.f, q0 = 0.f, q1 = 0.f;
#define STATS(j0, j1) _Pragma("unroll") for (int j = (j0); j < (j1); j++) { \
          uint32_t x[4]; \
          ldsm_x4(ta[j & 3] + (j >> 2) * SLOT, x[0], x[1], x[2], x[3]); \
          if (j == 0) { p0 = __shfl_sync(0xffffffffu, bf_lo(x[0]), lane & 28); p1 = __shfl_sync(0xffffffffu, bf_lo(x[1]), lane & 28); } \
          _Pragma("unroll") for (int i = 0; i < 4; i += 2) { \
            const float d0 = bf_lo(x[i]) - p0, d1 = bf_hi(x[i]) - p0, d2 = bf_lo(x[i + 1]) - p1, d3 = bf_hi(x[i + 1]) - p1; \
            a0 += d0 + d1; a1 += d2 + d3; \
            q0 = fmaf(d1, d1, fmaf(d0, d0, q0)); q1 = fmaf(d3, d3, fmaf(d2, d2, q1)); } } \
          asm volatile("" : "+f"(a0), "+f"(a1), "+f"(q0), "+f"(q1), "+f"(p0), "+f"(p1)); SCHED_FENCE()
        if (SB0) { STATS(0, SB0); }
        bar_wg(wg);
        QSTEP(S0, dA0 + ((OFF_S + SLOT) >> 4), 1, {});
        QREL();
        SCHED_FENCE();
        STATS(SB0, SB1);
        ACC_DEF(S1, 96);
        QSTEP(S1, dA0 + (OFF_S >> 4), 0, {});
        QREL();
        SCHED_FENCE();
        STATS(SB1, SB2);
        QSTEP(S1, dA0 + ((OFF_S + SLOT) >> 4), 1, {});
        QREL();
        SCHED_FENCE();
        STATS(SB2, SB3);
        if (SB3 < 8) {
          if (l) { asm volatile("cp.async.bulk.wait_group 0;" ::: "memory"); bar_arrive<BAR_X1, 288>(); }
          QSTEP(S0, RA_CUR, 1, {});
          SCHED_FENCE();
          STATS(SB3, 8);
          QREL();
        }
#pragma unroll
        for (int o = 1; o <= 2; o <<= 1) {
          a0 += __shfl_xor_sync(0xffffffffu, a0, o); a1 += __shfl_xor_sync(0xffffffffu, a1, o);
          q0 += __shfl_xor_sync(0xffffffffu, q0, o); q1 += __shfl_xor_sync(0xffffffffu, q1, o);
        }
        if (t == 1) { a0 = a1; q0 = q1; p0 = p1; }
        if (t < 2) st_b64(g_stats + (size_t)(mm * 128 + r0 + g + t * 8) * 8 + jj, __float_as_uint(fmaf(a0, 1.f / 128.f, p0)),
                          (__float_as_uint(fmaxf(fmaf(a0 * (-1.f / 128.f), a0, q0), 0.f)) & ~3u) | STAT_TAG(l));
        if (SB3 == 8 && l) { asm volatile("cp.async.bulk.wait_group 0;" ::: "memory"); bar_arrive<BAR_X1, 288>(); }
#pragma unroll 1
        for (int i = (SB3 < 8); i < 14; i++) {
          QSTEP(S0, RA_CUR, 1, {});
          if (i == 0) PROF(2);
          QREL();
        }
      }
      LANE_CONSTS();
      mbar_wait(bar_stat, par);
      LNSTEP(S0, 0);
      wgmma_commit();
      const float rs0 = lds32f(sbase + OFF_ST + (r0 + g) * 4), rs1 = lds32f(sbase + OFF_ST + (r0 + g + 8) * 4);
      PUMP0();
      ACC_FENCE(S0, 96);
      PROF(3);
      if (!par) {
        constexpr uint32_t par = 0;
        uint32_t qa[16];
        uint32_t kf[32], vf[32];
#define DRAIN_A(ACC, hp, PMP) { \
          LANE_CONSTS(); \
          FRAG(kf + 16, ACC + 32, 0, (hp) * 2); \
          PMP; \
          FRAG(vf + 16, ACC + 64, 1, (hp) * 2 + 1); \
          _Pragma("unroll") for (int i_ = 0; i_ < 16; i_++) qa[i_] = pack_bf16(ACC[2 * i_], ACC[2 * i_ + 1]); \
          PINU(qa, 16); }
        DRAIN_A(S0, 0, PUMP0());
        if (l == 0 && NLAYERS > 1) {
#pragma unroll 1
          for (int rd = 1; rd >= 0; rd--) {
            FOLD(sbase + (12 - rd) * SLOT, rd);
            fence_proxy_async_smem();
            asm volatile("bar.arrive %0, 288;" :: "r"(BAR_WF + 1 - rd) : "memory");
          }
        }
        PUMPS(FPUMP);
        if (l == 0 && NLAYERS > 1) mbar_wait(bar_phi, 1);
#pragma unroll 1
        for (int h = 0; h < 2; h++) {
          const uint32_t pO = sbase + (h ? 3 : 12) * SLOT;
          PROF(4 + h * 12);
          LANE_CONSTS();
          if (XA && h) {
            float T_[64];
            ACC_DEF(T_, 64);
            if (XA == 2) { FRAG_PUT(kf + 16, 10); }
            XM_ISSUE(0); wgmma_commit();
            SCHED_FENCE();
            if (XA == 1) { FRAG_PUT(kf + 16, 10); }
            FRAG_PUT(vf + 16, 11);
            STG_ARRIVE();
            SCHED_FENCE();
            wgmma_wait<0>(); XM_DONE(true);
          } else {
            FRAG_PUT(kf + 16, 10); FRAG_PUT(vf + 16, 11);
            STG_ARRIVE();
          }
          if (h) { if (!XA) LOAD_X(); if (AW0) WSTEP(); } else PUMPS(HPUMP2 + (wg == ALAG ? (l ? ADEL : ADEL0) : 0));
          const bool e = g & 1, hb = (2 * t + (g & 1)) <= g;
          uint32_t sel[3] = {e ? 0x1044u : 0x4410u, hb ? 0x4444u : (e ? 0x3244u : 0x4432u), hb ? (e ? 0x3244u : 0x4432u) : 0x4444u};
          PINU(sel, 3);
          TILE_CONSTS(pO, true, O_BIT(l));
          const uint32_t selA = sel[0], selL = sel[1], selH = sel[2];
          STG_WAIT();
          if (warp == 0) mbar_wait(bar_halo, h);
          FRAG_GET(kf, 10);
          PROF(5 + h * 12);
          float s[2][4][4];
#pragma unroll
          for (int ks = 0; ks < 2; ks++)
#pragma unroll
            for (int i = 0; i < 8; i++) {
              const int hh = (i >> 1) & 1, jb = (i & 1) + (~i >> 1 & 2);
              const uint32_t* b = kf + (jb >> 1) * 16 + hh * 8 + ks * 4 + (jb & 1) * 2;
              if (ks) mma_bf16(s[hh][jb], qa[hh * 8 + 4], qa[hh * 8 + 5], qa[hh * 8 + 6], qa[hh * 8 + 7], b[0], b[1]);
              else mma_bf16_z(s[hh][jb], qa[hh * 8], qa[hh * 8 + 1], qa[hh * 8 + 2], qa[hh * 8 + 3], b[0], b[1]);
            }
          PUMP();
          PROF(6 + h * 12);
          float va[2][2], vb[2][2], mx[2][2];
#pragma unroll
          for (int hh = 0; hh < 2; hh++) {
            va[hh][0] = e ? s[hh][1][1] : s[hh][1][0];
            vb[hh][0] = hb ? (e ? s[hh][2][1] : s[hh][2][0]) : (e ? s[hh][0][1] : s[hh][0][0]);
            va[hh][1] = e ? s[hh][2][3] : s[hh][2][2];
            vb[hh][1] = hb ? (e ? s[hh][3][3] : s[hh][3][2]) : (e ? s[hh][1][3] : s[hh][1][2]);
          }
          if (warp == 0 && mm == 0) {
#pragma unroll
            for (int hh = 0; hh < 2; hh++) { va[hh][0] = -INFINITY; if (!hb) { vb[hh][0] = -INFINITY; vb[hh][1] = -INFINITY; } }
          }
#pragma unroll
          for (int i = 0; i < 4; i++) mx[i >> 1][i & 1] = fmaxf(va[i >> 1][i & 1], vb[i >> 1][i & 1]);
#pragma unroll
          for (int o = 1; o <= 2; o <<= 1)
#pragma unroll
            for (int i = 0; i < 4; i++) mx[i >> 1][i & 1] = fmaxf(mx[i >> 1][i & 1], __shfl_xor_sync(0xffffffffu, mx[i >> 1][i & 1], o));
          const float sc0 = rs0 * (0.17677669529663687f * LOG2E), sc1 = rs1 * (0.17677669529663687f * LOG2E);
#pragma unroll
          for (int i = 0; i < 4; i++) {
            const float sc = (i & 1) ? sc1 : sc0, m = mx[i >> 1][i & 1];
            va[i >> 1][i & 1] = ex2((va[i >> 1][i & 1] - m) * sc); vb[i >> 1][i & 1] = ex2((vb[i >> 1][i & 1] - m) * sc);
            mx[i >> 1][i & 1] = va[i >> 1][i & 1] + vb[i >> 1][i & 1];
          }
          if (h == 0 && ASITE) { PIN(&va[0][0], 4); PIN(&vb[0][0], 4); PIN(&mx[0][0], 4); PUMP1(); }
          if (warp == 0) mbar_wait(bar_halo + 8, h);
          FRAG_GET(vf, 11);
#pragma unroll
          for (int o = 1; o <= 2; o <<= 1)
#pragma unroll
            for (int i = 0; i < 4; i++) mx[i >> 1][i & 1] += __shfl_xor_sync(0xffffffffu, mx[i >> 1][i & 1], o);
          float o[2][4][4];
          uint32_t pa[2][8];
#pragma unroll
          for (int hh = 0; hh < 2; hh++) {
            const float i0 = rcp_fast(mx[hh][0]), i1 = rcp_fast(mx[hh][1]);
            const uint32_t w0 = pack_bf16(va[hh][0] * i0, vb[hh][0] * i0), w1 = pack_bf16(va[hh][1] * i1, vb[hh][1] * i1);
            pa[hh][0] = __byte_perm(w0, 0, selL); pa[hh][2] = __byte_perm(w0, 0, selA); pa[hh][3] = __byte_perm(w1, 0, selL);
            pa[hh][4] = __byte_perm(w0, 0, selH); pa[hh][5] = __byte_perm(w1, 0, selA); pa[hh][7] = __byte_perm(w1, 0, selH);
            pa[hh][1] = pa[hh][0] & pa[hh][4]; pa[hh][6] = pa[hh][3] & pa[hh][7];
          }
          PROF(7 + h * 12);
#pragma unroll
          for (int i = 0; i < 8; i++) mma_bf16_z(o[i >> 2][i & 3], pa[i >> 2][4], pa[i >> 2][5], pa[i >> 2][6], pa[i >> 2][7], vf[16 + 2 * i], vf[17 + 2 * i]);
#pragma unroll
          for (int i = 0; i < 8; i++) mma_bf16(o[i >> 2][i & 3], pa[i >> 2][0], pa[i >> 2][1], pa[i >> 2][2], pa[i >> 2][3], vf[2 * i], vf[2 * i + 1]);
          if (h == 0) PUMP1() else mbar_wait(bar_done + 30 * 8, par);
          if (NLAYERS > 1) mbar_wait(bar_phi + 8, 0);
#pragma unroll
          for (int i = 0; i < 4; i++) {
            const int hh = i >> 1, dp = i & 1;
            stsm_x4(ta[i],
                    PBIT0(pack_bf16(o[hh][dp * 2][0], o[hh][dp * 2][1])), PBIT0(pack_bf16(o[hh][dp * 2][2], o[hh][dp * 2][3])),
                    PBIT1(pack_bf16(o[hh][dp * 2 + 1][0], o[hh][dp * 2 + 1][1])), PBIT1(pack_bf16(o[hh][dp * 2 + 1][2], o[hh][dp * 2 + 1][3])));
          }
          PUBLISH_O();
          PROF(11 + h * 12);
          if (h) break;
          REST_P1(ASKEW);
          asm volatile("cp.async.bulk.wait_group.read 0;" ::: "memory");
          DRAIN_A(S1, 1, {});
        }
      } else {
        constexpr uint32_t par = 1;
        float st[32];
        const float c0 = rs0 * LOG2E, c1 = rs1 * LOG2E;
        { V_ADDR(pV); STAGE_V(S0 + 64); }
        if (warp < 2) sts128(sbase + OFF_ONES + warp * 512 + lane * 16, 0x3F803F80u, 0x3F803F80u, 0x3F803F80u, 0x3F803F80u);
        scale32(st, S0, c0, c1);
        PIN(st, 32);
#define KV_MMA(vs) { \
          const uint32_t dp = dA0 + 12 * 1024 - wg * 2560, dv = dA0 + (vs) * 1024 + ((OFF_ONES - (vs) * SLOT - 16) << 12) - wg * (512 << 16); \
          STG_WAIT(); \
          wgmma_fence(); \
          _Pragma("unroll") for (int ks = 0; ks < 8; ks++) { \
            const uint64_t a = DESC(dp + ks * 128, 0x40000040), b = DESC(dv + ks * (64 - (64 << 16)), 0x80000020); \
            if (ks == 0) wgmma_n40<0, 1>(kv, a, b); else wgmma_n40<1, 1>(kv, a, b); } \
          wgmma_commit(); }
#define KV_RED(hp) { \
          float* kvg = g_kv[l >> 1] + (jj * 4 + (hp) * 2) * KVH + warp * 768 + lane * 4; \
          _Pragma("unroll") for (int i = 0; i < 5; i++) red_v4(kvg + i * 128, kv[i * 3], kv[i * 3 + 1], kv[i * 3 + 2], 1.f); \
          red_v4(kvg + 640, kv[15], kv[16], kv[18], 1.f); }
#define KV_LOAD(hp) { \
          const uint4* kvg = reinterpret_cast<const uint4*>(g_kv[l >> 1] + (jj * 4 + (hp) * 2) * KVH) + warp * 192 + lane; \
          _Pragma("unroll") for (int i = 0; i < 6; i++) v[i] = ld_b128(kvg + i * 32); }
#define KVV(i) __uint_as_float((i) % 3 == 0 ? v[(i) / 3].x : ((i) % 3 == 1 ? v[(i) / 3].y : v[(i) / 3].z))
#define KV_TILE(hp) { \
          _Pragma("unroll 1") for (int it = 0; it < (1 << 16); it++) { \
            if (__all_sync(0xffffffffu, (v[0].w & v[1].w & v[2].w & v[3].w & v[4].w & v[5].w) == 0x41800000u)) break; \
            RETRY_COUNT(); \
            KV_LOAD(hp); \
          } \
          PROF(25 + (hp)); \
          const uint32_t e = lane & 7, jt = ((lane >> 1) & 4) + (e >> 1); \
          const uint32_t row = ((((warp >> 1) ^ wg) & 1) << 5) + ((jt & 1) << 4) + ((warp & 1) << 3) + (jt & 6) + (e & 1); \
          const uint32_t kd = pV + wg * 8192 + row * 128, ksw = (row & 7) << 4; \
          _Pragma("unroll") for (int i = 0; i < 2; i++) \
            stsm_x4(kd + ((i * 32 + lhi) ^ ksw), pack_bf16(KVV(i * 8), KVV(i * 8 + 1)), pack_bf16(KVV(i * 8 + 2), KVV(i * 8 + 3)), \
                    pack_bf16(KVV(i * 8 + 4), KVV(i * 8 + 5)), pack_bf16(KVV(i * 8 + 6), KVV(i * 8 + 7))); \
          stsm_x4(kd + ((64u + lhi) ^ ksw), pack_bf16(KVV(16), 1.f), pack_bf16(KVV(17), 1.f), 0u, 0u); }
#pragma unroll 1
        for (int h = 0; h < 2; h++) {
          PROF(4 + h * 2);
          SITE(0);
          LANE_CONSTS();
          const uint32_t dsw = (uint32_t)(g ^ (2 * t)) << 4, dst = ((t & 2) ? pK : sbase + 12 * SLOT) + (r0 + g) * 128;
          float e[16], f[16];
          float sa = exps16_<0>(e, st);
          exps16_fix<0>(e, st, sa);
          asm volatile("" : "+f"(sa)); PIN(e, 16); SITE(1);
          if (h) STG_WAIT();
          store16(e, sa, dst, dsw, 4);
          float sb = exps16_<1>(f, st);
          exps16_fix<1>(f, st, sb);
          asm volatile("" : "+f"(sb)); PIN(f, 16); SITE(2);
          store16(f, sb, dst, dsw, 0);
          float sc = exps16_<0>(e, st + 2);
          exps16_fix<0>(e, st + 2, sc);
          asm volatile("" : "+f"(sc)); PIN(e, 16); SITE(3);
          store16(e, sc, dst + 1024, dsw, 4);
          float sd = exps16_<1>(f, st + 2);
          exps16_fix<1>(f, st + 2, sd);
          asm volatile("" : "+f"(sd)); PIN(f, 16); SITE(4);
          store16(f, sd, dst + 1024, dsw, 0);
          PROF(5 + h * 2);
          if (h) break;
          {
            float kv[20];
            ACC_DEF(kv, 20);
            fence_proxy_async_smem();
            STG_ARRIVE();
            KV_MMA(11);
            PUMP0();
            ACC_FENCE(kv, 20);
            KV_RED(0);
            STG_ARRIVE();
          }
          scale32(st, S0 + 32, c0, c1);
          PIN(st, 32);
        }
        bool big;
        uint4 v[6];
        {
          float kv[20];
          if (KT0) { LANE_CONSTS(); KV_LOAD(0); }
          mbar_wait(bar_stat2, par);
          LNSTEP(S1, 1);
          ub = bar_full + 240;
          PUMP1();
          if (wg == 0) bar_sync<BAR_SKEW, 256>();
          QSTEP(S1, RA_CUR, 1, {});
          if (wg == 1) bar_arrive<BAR_SKEW, 256>();
          QREL();
          if (KT0 == 2) { LANE_CONSTS(); KV_TILE(0); }
          LANE_CONSTS();
          V_ADDR(sbase + 3 * SLOT);
          PINU(va_, 2);
          mbar_wait(bar_done + 30 * 8, par);
          wgmma_wait<0>();
          ACC_FENCE(S1, 96);
          if (!(RLATE & 2)) REL(bar_done + 31 * 8);
          PROF(13);
          STAGE_V(S1 + 64);
          fence_proxy_async_smem();
          STG_ARRIVE();
          if (RLATE & 2) REL(bar_done + 31 * 8);
          scale32(st, S1, c0, c1);
          PIN(st, 32);
          PROF(16);
          ACC_DEF(kv, 20);
          KV_MMA(3);
          SCHED_FENCE();
          if (!KT0) KV_LOAD(0);
          big = any_big(st);
          if (EROT > 0) { phiq_a(st, big); PIN(st, 16); }
          SCHED_FENCE();
          wgmma_wait<0>();
          ACC_FENCE(kv, 20);
          KV_RED(1);
          PROF(17);
        }
#pragma unroll 1
        for (int h = 0; h < 2; h++) {
          const uint32_t pO = sbase + (h ? 3 : 8) * SLOT;
          LANE_CONSTS();
          uint32_t fq[32];
          if (EROT < 1) phiq_a(st, big);
          if (EMRG == 0) { phiq_b<0>(fq, st, big); PINU(fq, 16); }
          if (EMRG == 2) { phiq_b<1>(fq, st, big); PINU(fq, 16); PIN(st + 16, 16); }
          PROF(18 + h * 14);
          SCHED_FENCE();
          if (h) {
            asm volatile("cp.async.bulk.wait_group.read 0;" ::: "memory");
            mbar_wait(bar_lx, par);
          }
          if (h || KT0 < 2) {
            KV_TILE(h);
            fence_proxy_async_smem();
            STG_ARRIVE();
          }
          SCHED_FENCE();
          if (EMRG == 0) { phiq_a(st + 16, big); PIN(st + 16, 16); }
          if (EMRG == 1) { phiq_b<1>(fq, st, big); PINU(fq, 16); PIN(st + 16, 16); }
          if (h || KT0 < 2) STG_WAIT();
          wgmma_wait<0>();
          ACC_FENCE(S1, 64);
          float T_[64];
          if (XB == 3) { COPY64(T_, S1); }
          PROF(19 + h * 14);
          float o[4][20];
#define O_MMA(hh) { \
            const uint64_t db = make_desc(pV + (hh) * 8192, 16, 1024); \
            ACC_DEF(o[(hh) * 2], 20); ACC_DEF(o[(hh) * 2 + 1], 20); \
            wgmma_fence(); \
            wgmma_n40_rs<0>(o[(hh) * 2], fq + (hh) * 16, db + 256); wgmma_n40_rs<0>(o[(hh) * 2 + 1], fq + (hh) * 16 + 8, db); \
            wgmma_n40_rs<1>(o[(hh) * 2], fq + (hh) * 16 + 4, db + 384); wgmma_n40_rs<1>(o[(hh) * 2 + 1], fq + (hh) * 16 + 12, db + 128); \
            wgmma_commit(); }
          O_MMA(0);
          SCHED_FENCE();
          phiq_b<0>(fq + 16, st + 16, big); PINU(fq + 16, 16);
          SCHED_FENCE();
          PMASKS(true, O_BIT(l));
#pragma unroll
          for (int hh = 0; hh < 2; hh++) {
            if (hh && !OW) O_MMA(1);
            if (XB == 3 && hh) { scale32(st, T_ + 32, c0, c1); PIN(st, 32); XM_ISSUE(h); wgmma_commit(); wgmma_wait<1>(); } else
            wgmma_wait<0>();
            ACC_FENCE(o[hh * 2], 20); ACC_FENCE(o[hh * 2 + 1], 20);
            if (!hh && OW) { O_MMA(1); SCHED_FENCE(); }
            const float* x = o[hh * 2];
            const float* y = o[hh * 2 + 1];
            const float sx0 = x[17] * 0x1p-40f, sy0 = y[17] * 0x1p-40f, sx1 = x[19] * 0x1p-40f, sy1 = y[19] * 0x1p-40f;
            const float i0 = rcp_fast(fmaf(fmaf(x[17], 1e-6f, x[16]), sy0, y[16] * sx0)), i1 = rcp_fast(fmaf(fmaf(x[19], 1e-6f, x[18]), sy1, y[18] * sx1));
            const float ax0 = sy0 * i0, ay0 = sx0 * i0, ax1 = sy1 * i1, ay1 = sx1 * i1;
#pragma unroll
            for (int dp = 0; dp < 2; dp++)
              stsm_x4(pO + srowoff + ((hh * 64 + dp * 32 + lhi) ^ lsw),
                      PBIT0(pack_bf16(fmaf(x[dp * 8], ax0, y[dp * 8] * ay0), fmaf(x[dp * 8 + 1], ax0, y[dp * 8 + 1] * ay0))),
                      PBIT0(pack_bf16(fmaf(x[dp * 8 + 2], ax1, y[dp * 8 + 2] * ay1), fmaf(x[dp * 8 + 3], ax1, y[dp * 8 + 3] * ay1))),
                      PBIT1(pack_bf16(fmaf(x[dp * 8 + 4], ax0, y[dp * 8 + 4] * ay0), fmaf(x[dp * 8 + 5], ax0, y[dp * 8 + 5] * ay0))),
                      PBIT1(pack_bf16(fmaf(x[dp * 8 + 6], ax1, y[dp * 8 + 6] * ay1), fmaf(x[dp * 8 + 7], ax1, y[dp * 8 + 7] * ay1))));
          }
          PUBLISH_O();
          if (XB == 3) { wgmma_wait<0>(); XM_DONE(h == 0); }
          PROF(20 + h * 14);
          if (h) break;
          if (KVL == 2) { KV_LOAD(1); SCHED_FENCE(); }
          if (!XB) {
            scale32(st, S1 + 32, c0, c1);
            PIN(st, 32);
            LOAD_X();
          }
          if (XB == 4) {
            scale32(st, S1 + 32, c0, c1);
            PIN(st, 32);
            ACC_DEF(T_, 64);
            XM_ISSUE(0); wgmma_commit();
            SCHED_FENCE();
            KV_LOAD(1);
            big = any_big(st);
            SCHED_FENCE();
            wgmma_wait<0>(); XM_DONE(true);
          }
          bar_wg(wg);
          WSTEP();
          SCHED_FENCE();
          if (KVL == 0 && XB != 4) KV_LOAD(1);
          if (XB != 4) big = any_big(st);
          if (KVL == 1) { SCHED_FENCE(); KV_LOAD(1); }
          if (EROT > 0) { phiq_a(st, big); PIN(st, 16); }
          PROF(31);
        }
      }
      __syncwarp();
      if (elect_one()) mbar_arrive_local(bar_epi);
      bar_wg(wg);
#pragma unroll 1
      while (ub < bar_full + 384) {
        if (WHOLD && ub == bar_full + 8 * WHOLD && wg != WLEAD) bar_sync<11, 256>();
        WSTEPH(if (WHOLD && ub == bar_full + 8 * WREL && wg == WLEAD) { bar_arrive<11 COMMA 256>(); });
        if (ub == bar_full + 8 * 41) { asm volatile("cp.async.bulk.wait_group.read 0;" ::: "memory"); PROF(35); }
        if (ub == bar_full + 8 * 42) PROF(36);
      }
      {
        LANE_CONSTS();
        TILE_CONSTS(pK, l < NLAYERS - 1, X_BIT(l));
        wgmma_wait<0>();
        ACC_FENCE(S1, 64);
        if (!RLATE) REL(bar_done + 47 * 8);
        PROF(37);
        X_OUT(0);
        WARP_STORE(l < NLAYERS - 1 ? &tm_os : &tm_xo, pK, jj * 128, mm * 128 + (l < NLAYERS - 1 ? S_LEN : 0));
        if (RLATE) REL(bar_done + 47 * 8);
        if (l == NLAYERS - 1) {
          X_OUT(1);
          WARP_STORE(&tm_xo, pV, jj * 128 + 64, mm * 128);
          if (FINW) asm volatile("cp.async.bulk.wait_group 0;" ::: "memory"); else asm volatile("cp.async.bulk.wait_group.read 0;" ::: "memory");
        }
      }
#pragma unroll
      for (int i = 32; i < 64; i++) { uint32_t c; asm volatile("mov.b32 %0, %1;" : "=r"(c) : "f"(S1[i])); S1[i] = __uint_as_float(c); }
      PROF(38);
    }
    cluster_sync();
  }
}

typedef CUresult (*PFN_encode)(CUtensorMap*, CUtensorMapDataType, cuuint32_t, void*, const cuuint64_t*, const cuuint64_t*,
                               const cuuint32_t*, const cuuint32_t*, CUtensorMapInterleave, CUtensorMapSwizzle,
                               CUtensorMapL2promotion, CUtensorMapFloatOOBfill);

CUtensorMap make_map(PFN_encode enc, const void* ptr, uint64_t inner, uint64_t outer, uint32_t box_inner, uint32_t box_outer,
                     CUtensorMapSwizzle swz = CU_TENSOR_MAP_SWIZZLE_128B, int promo = CU_TENSOR_MAP_L2_PROMOTION_L2_256B) {
  CUtensorMap m;
  cuuint64_t dims[2] = {inner, outer};
  cuuint64_t strides[1] = {inner * 2};
  cuuint32_t box[2] = {box_inner, box_outer};
  cuuint32_t es[2] = {1, 1};
  enc(&m, CU_TENSOR_MAP_DATA_TYPE_BFLOAT16, 2, const_cast<void*>(ptr), dims, strides, box, es, CU_TENSOR_MAP_INTERLEAVE_NONE,
      swz, (CUtensorMapL2promotion)promo, CU_TENSOR_MAP_FLOAT_OOB_FILL_NONE);
  return m;
}

}

extern "C" void kernel_launch(void* const* d_in, const int* in_sizes, int n_in, void* d_out, int out_size) {
  (void)in_sizes; (void)n_in; (void)out_size;
  static PFN_encode enc = nullptr;
  if (!enc) {
    void* fn = nullptr;
    cudaDriverEntryPointQueryResult qr;
    cudaGetDriverEntryPoint("cuTensorMapEncodeTiled", &fn, cudaEnableDefault, &qr);
    enc = (PFN_encode)fn;
    cudaFuncSetAttribute(mega_kernel, cudaFuncAttributeMaxDynamicSharedMemorySize, SMEM_BYTES);
  }
  Params prm;
  prm.x0 = (const __nv_bfloat16*)d_in[0];
  prm.wA_qkv = (const __nv_bfloat16*)d_in[1];
  prm.wA_o = (const __nv_bfloat16*)d_in[2];
  prm.wB_qkv = (const __nv_bfloat16*)d_in[4];
  prm.wB_phi = (const __nv_bfloat16*)d_in[5];
  prm.wB_o = (const __nv_bfloat16*)d_in[6];
  prm.out = (__nv_bfloat16*)d_out;
  void *obuf = nullptr, *wf = nullptr;
  cudaGetSymbolAddress(&obuf, g_obuf);
  cudaGetSymbolAddress(&wf, g_wfold);
  CUtensorMap tm_x0 = make_map(enc, d_in[0], D_MODEL, S_LEN, 64, 128, CU_TENSOR_MAP_SWIZZLE_128B, XPROMO);
  CUtensorMap tm_xo = make_map(enc, d_out, D_MODEL, S_LEN, 64, 16);
  CUtensorMap tm_os = make_map(enc, obuf, D_MODEL, 2 * S_LEN, 64, 16);
  CUtensorMap tm_o = make_map(enc, obuf, D_MODEL, 2 * S_LEN, 64, 128, CU_TENSOR_MAP_SWIZZLE_128B, OPROMO);
  CUtensorMap tm_wf = make_map(enc, wf, 2048, D_MODEL, 64, 32);
  CUtensorMap tm_wqA = make_map(enc, d_in[1], 3 * D_MODEL, D_MODEL, 64, 32, CU_TENSOR_MAP_SWIZZLE_128B, WPROMO);
  CUtensorMap tm_wqB = make_map(enc, prm.wB_qkv, 3 * D_MODEL, D_MODEL, 64, 32);
  CUtensorMap tm_woA = make_map(enc, prm.wA_o, D_MODEL, D_MODEL, 64, 64);
  CUtensorMap tm_woB = make_map(enc, prm.wB_o, D_MODEL, D_MODEL, 64, 64);
  CUtensorMap tm_phi = make_map(enc, prm.wB_phi, 32, 1024, 32, 128, CU_TENSOR_MAP_SWIZZLE_64B);
  mega_kernel<<<NMAIN + NAUX, 384, SMEM_BYTES>>>(tm_x0, tm_xo, tm_os, tm_o, tm_wf, tm_wqA, tm_wqB, tm_woA, tm_woB, tm_phi, prm);
}
```

```cpp
#include <cuda_runtime.h>
#include <cuda.h>
#include <cuda_bf16.h>
#include <stdint.h>

#define NLAYERS 4

#define STAG1 0
#define HPUMP1 2
#define HPUMP2 1
#define ASKEW 2
#define FPUMP 3
#define PFGAP 100
#define POLLGAP 120
#define OW 1
#define AW0 1
#define RLATE 3
#define FSTART 0
#define MAPV 1
#define HW1 29
#define XPACE 0x06050401000000ull
#define XP0 4
#define HW0 18
#define XD 4
#define WFGAP 50
#define KT0 2
#define W23 0
#define AX 0
#define PF0 1
#define EARLY 2
#define BIGLIM 3600.f
#define SUMLO 0x1p-100f
#define SUMHI 0x1p100f
#define EROT 1
#define FINW 0
#define AHOIST 1
#define EMRG 1
#define XPROMO 2
#define OPROMO 3
#define STAG2 300
#define WPROMO 3
#define SB0 2
#define SB1 4
#define SB2 6
#define SB3 8
#define KVL 0
#define BMASK 0x1F
#define ASITE 1
#define NEWOPTS
#define RPACE 0x221100
#define XA 0
#define XB 4
#define XMMA 1
namespace {

constexpr int S_LEN = 2048, D_MODEL = 1024;
constexpr int NAUX = 4, NMAIN = 128;
constexpr int SLOT = 16384;
constexpr int QST = 24576;
constexpr int OFF_RA = 6 * SLOT, OFF_S = 10 * SLOT;
constexpr int OFF_HALO = 13 * SLOT, OFF_LNB = OFF_HALO  , OFF_ONES = OFF_HALO + 3072;
constexpr int OFF_ST = OFF_HALO + 7168  , OFF_ID = OFF_HALO + 7680, OFF_PHI = OFF_HALO + 8192;
constexpr int OFF_BAR = 14 * SLOT;
constexpr int OFF_LNA = OFF_BAR + 1024;
constexpr int SMEM_BYTES = OFF_LNA + 2048;
#define WO_ASLOT(par) ((par) ? 0x9876CAB39876CA98ull : 0x98C76BA398C7698Cull)
constexpr unsigned long long WO_BSLOT = 0x5432105421054210ull;
__device__ __forceinline__ int srcb(int j, int i) { return (i + (i >= j)) & 7; }
__device__ __forceinline__ int kslice(int j, int i) { return i < 2 ? 2 * j + i : (i < 9 ? 2 * srcb(j, i - 2) : 2 * srcb(j, i - 9) + 1); }
__device__ __forceinline__ int wslice(int j, int s) { return 2 * ((s & 7) ? srcb(j, (s & 7) - 1) : j) + (s >> 3); }
constexpr int KVH = 6 * 128 * 4;

struct __align__(128) Flag { unsigned v; unsigned pad[31]; };
struct Flags {
  Flag xready[4][16];
  Flag wfready[8];
  Flag done;
  Flag epoch;
};

__device__ Flags g_flags;
__device__ __nv_bfloat16 g_obuf[2 * S_LEN * D_MODEL];
#define O_BIT(l) ((epoch * NLAYERS + (l) + 1) & 1u)
#define X_BIT(l) ((epoch * (NLAYERS - 1) + (l) + 1) & 1u)
__device__ __nv_bfloat16 g_wfold[D_MODEL * 2048];
__device__ uint4 g_halo[16 * 8 * 512];
__device__ __align__(128) float g_kv[2][32 * KVH];
__device__ __align__(128) uint2 g_colsum[2][1536][2];
__device__ __align__(128) uint2 g_stats[S_LEN * 8];
#define H_BIT(l) (NLAYERS > 2 ? (uint32_t)((l) == 0) : (ep1 & 1))
#define STAT_TAG(l) ((ep1 * NLAYERS + (l) + 1) & 3u)

#define RETRY_COUNT()
#define PRL 0
#define PRU 0
#define PROFL 1
#define PROFW 0
#define PROFT(i) do {} while (0)
#define PROF(i) do {} while (0)
#define PROFH(i, j) do {} while (0)

__device__ __forceinline__ uint32_t smem_u32(const void* p) { return (uint32_t)__cvta_generic_to_shared(p); }
__device__ __forceinline__ bool elect_one() {
  uint32_t p;
  asm volatile("{\n.reg .pred p;\nelect.sync _|p, 0xffffffff;\nselp.u32 %0, 1, 0, p;\n}\n" : "=r"(p));
  return p != 0;
}
__device__ __forceinline__ void mbar_init(uint32_t bar, uint32_t cnt) {
  asm volatile("mbarrier.init.shared::cta.b64 [%0], %1;" :: "r"(bar), "r"(cnt));
}
__device__ __forceinline__ void mbar_expect_tx(uint32_t bar, uint32_t bytes) {
  asm volatile("mbarrier.arrive.expect_tx.shared::cta.b64 _, [%0], %1;" :: "r"(bar), "r"(bytes) : "memory");
}
#define mbar_wait(bar, parity) \
  asm volatile("{\n.reg .pred p, q;\nW_%=:\nmbarrier.try_wait.parity.shared::cta.b64 p, [%1], %2;\nadd.s32 %0, %0, -1;\n" \
               "setp.gt.and.s32 q, %0, 0, !p;\n@q bra.uni W_%=;\n}\n" : "+r"(budget) : "r"((uint32_t)(bar)), "r"((uint32_t)(parity)) : "memory")
#define mbar_wait_sl(bar, parity) \
  asm volatile("{\n.reg .pred p, q;\nW_%=:\nmbarrier.try_wait.parity.shared::cta.b64 p, [%1], %2, 20000;\nadd.s32 %0, %0, -64;\n" \
               "setp.gt.and.s32 q, %0, 0, !p;\n@q bra.uni W_%=;\n}\n" : "+r"(budget) : "r"((uint32_t)(bar)), "r"((uint32_t)(parity)) : "memory")
__device__ __forceinline__ void mbar_arrive_local(uint32_t bar) {
  asm volatile("mbarrier.arrive.shared::cta.b64 _, [%0];" :: "r"(bar) : "memory");
}
__device__ __forceinline__ void tma_load_2d(uint32_t dst, const CUtensorMap* tm, uint32_t bar, int c0, int c1) {
  asm volatile("cp.async.bulk.tensor.2d.shared::cluster.global.mbarrier::complete_tx::bytes [%0], [%1, {%3, %4}], [%2];"
               :: "r"(dst), "l"(tm), "r"(bar), "r"(c0), "r"(c1) : "memory");
}
__device__ __forceinline__ void tma_load_2d_mc(uint32_t dst, const CUtensorMap* tm, uint32_t bar, int c0, int c1) {
  asm volatile("cp.async.bulk.tensor.2d.shared::cluster.global.mbarrier::complete_tx::bytes.multicast::cluster [%0], [%1, {%3, %4}], [%2], %5;"
               :: "r"(dst), "l"(tm), "r"(bar), "r"(c0), "r"(c1), "h"((uint16_t)3) : "memory");
}
__device__ __forceinline__ void tma_store_2d(const CUtensorMap* tm, uint32_t src, int c0, int c1) {
  asm volatile("cp.async.bulk.tensor.2d.global.shared::cta.bulk_group [%0, {%2, %3}], [%1];"
               :: "l"(tm), "r"(src), "r"(c0), "r"(c1) : "memory");
}
__device__ __forceinline__ void bulk_commit_wait() {
  asm volatile("cp.async.bulk.commit_group;\ncp.async.bulk.wait_group 0;" ::: "memory");
}
__device__ __forceinline__ void prefetch_tmap(const CUtensorMap* tm) {
  asm volatile("prefetch.tensormap [%0];" :: "l"(tm) : "memory");
}
__device__ __forceinline__ void fence_proxy_async_global() { asm volatile("fence.proxy.async.global;" ::: "memory"); }
__device__ __forceinline__ void fence_proxy_async_smem() { asm volatile("fence.proxy.async.shared::cta;" ::: "memory"); }
__device__ __forceinline__ unsigned ld_relaxed(const unsigned* p) {
  unsigned v;
  asm volatile("ld.relaxed.gpu.global.u32 %0, [%1];" : "=r"(v) : "l"(p) : "memory");
  return v;
}
__device__ __forceinline__ void fence_acquire() { asm volatile("fence.acquire.gpu;" ::: "memory"); }
__device__ __forceinline__ void wait_flag(const unsigned* p, unsigned target) {
  int it = 0;
  while ((int)(ld_relaxed(p) - target) < 0 && ++it < (1 << 20)) {}
  fence_acquire();
}
__device__ __forceinline__ void signal_release(unsigned* p) {
  asm volatile("red.release.gpu.global.add.u32 [%0], 1;" :: "l"(p) : "memory");
}
template <int ID, int N> __device__ __forceinline__ void bar_arrive() { asm volatile("bar.arrive %0, %1;" :: "n"(ID), "n"(N) : "memory"); }
template <int ID, int N> __device__ __forceinline__ void bar_sync() { asm volatile("bar.sync %0, %1;" :: "n"(ID), "n"(N) : "memory"); }
__device__ __forceinline__ void bar_wg(int wg) { asm volatile("bar.sync %0, 128;" :: "r"(2 + wg) : "memory"); }
__device__ __forceinline__ void cluster_sync() {
  asm volatile("barrier.cluster.arrive.relaxed.aligned;\nbarrier.cluster.wait.aligned;" ::: "memory");
}
__device__ __forceinline__ void cluster_wait() { asm volatile("barrier.cluster.wait.acquire.aligned;" ::: "memory"); }
enum { BAR_X1 = 7, BAR_WF = 8  , BAR_SKEW = 10 };

__device__ __forceinline__ void wgmma_fence() { asm volatile("wgmma.fence.sync.aligned;" ::: "memory"); }
__device__ __forceinline__ void wgmma_commit() { asm volatile("wgmma.commit_group.sync.aligned;" ::: "memory"); }
template <int N> __device__ __forceinline__ void wgmma_wait() { asm volatile("wgmma.wait_group.sync.aligned %0;" :: "n"(N) : "memory"); }

template <int scale_d, int tnsp_b = 1> __device__ __forceinline__ void wgmma_n192(float* d, uint64_t descA, uint64_t descB) {
  asm volatile("{\n.reg .pred p;\nsetp.ne.b32 p, %98, 0;\n"
               "wgmma.mma_async.sync.aligned.m64n192k16.f32.bf16.bf16 {%0,%1,%2,%3,%4,%5,%6,%7,%8,%9,%10,%11,%12,%13,%14,%15,%16,%17,%18,%19,%20,%21,%22,%23,%24,%25,%26,%27,%28,%29,%30,%31,%32,%33,%34,%35,%36,%37,%38,%39,%40,%41,%42,%43,%44,%45,%46,%47,%48,%49,%50,%51,%52,%53,%54,%55,%56,%57,%58,%59,%60,%61,%62,%63,%64,%65,%66,%67,%68,%69,%70,%71,%72,%73,%74,%75,%76,%77,%78,%79,%80,%81,%82,%83,%84,%85,%86,%87,%88,%89,%90,%91,%92,%93,%94,%95}, %96, %97, p, 1, 1, 0, %99;\n}\n"
               : "+f"(d[0]), "+f"(d[1]), "+f"(d[2]), "+f"(d[3]), "+f"(d[4]), "+f"(d[5]), "+f"(d[6]), "+f"(d[7]), "+f"(d[8]), "+f"(d[9]), "+f"(d[10]), "+f"(d[11]), "+f"(d[12]), "+f"(d[13]), "+f"(d[14]), "+f"(d[15]), "+f"(d[16]), "+f"(d[17]), "+f"(d[18]), "+f"(d[19]), "+f"(d[20]), "+f"(d[21]), "+f"(d[22]), "+f"(d[23]), "+f"(d[24]), "+f"(d[25]), "+f"(d[26]), "+f"(d[27]), "+f"(d[28]), "+f"(d[29]), "+f"(d[30]), "+f"(d[31]), "+f"(d[32]), "+f"(d[33]), "+f"(d[34]), "+f"(d[35]), "+f"(d[36]), "+f"(d[37]), "+f"(d[38]), "+f"(d[39]), "+f"(d[40]), "+f"(d[41]), "+f"(d[42]), "+f"(d[43]), "+f"(d[44]), "+f"(d[45]), "+f"(d[46]), "+f"(d[47]), "+f"(d[48]), "+f"(d[49]), "+f"(d[50]), "+f"(d[51]), "+f"(d[52]), "+f"(d[53]), "+f"(d[54]), "+f"(d[55]), "+f"(d[56]), "+f"(d[57]), "+f"(d[58]), "+f"(d[59]), "+f"(d[60]), "+f"(d[61]), "+f"(d[62]), "+f"(d[63]), "+f"(d[64]), "+f"(d[65]), "+f"(d[66]), "+f"(d[67]), "+f"(d[68]), "+f"(d[69]), "+f"(d[70]), "+f"(d[71]), "+f"(d[72]), "+f"(d[73]), "+f"(d[74]), "+f"(d[75]), "+f"(d[76]), "+f"(d[77]), "+f"(d[78]), "+f"(d[79]), "+f"(d[80]), "+f"(d[81]), "+f"(d[82]), "+f"(d[83]), "+f"(d[84]), "+f"(d[85]), "+f"(d[86]), "+f"(d[87]), "+f"(d[88]), "+f"(d[89]), "+f"(d[90]), "+f"(d[91]), "+f"(d[92]), "+f"(d[93]), "+f"(d[94]), "+f"(d[95])
               : "l"(descA), "l"(descB), "n"(scale_d), "n"(tnsp_b));
}
template <int scale_d> __device__ __forceinline__ void wgmma4_n192(float* d, uint32_t da, uint32_t db) {
#define R_ "{%0,%1,%2,%3,%4,%5,%6,%7,%8,%9,%10,%11,%12,%13,%14,%15,%16,%17,%18,%19,%20,%21,%22,%23,%24,%25,%26,%27,%28,%29,%30,%31,%32,%33,%34,%35,%36,%37,%38,%39,%40,%41,%42,%43,%44,%45,%46,%47,%48,%49,%50,%51,%52,%53,%54,%55,%56,%57,%58,%59,%60,%61,%62,%63,%64,%65,%66,%67,%68,%69,%70,%71,%72,%73,%74,%75,%76,%77,%78,%79,%80,%81,%82,%83,%84,%85,%86,%87,%88,%89,%90,%91,%92,%93,%94,%95}"
  asm volatile("{\n.reg .pred p, q;\n.reg .b64 a, b;\nsetp.ne.b32 p, %98, 0;\nsetp.eq.b32 q, 0, 0;\nmov.b64 a, {%96, 0x40000040};\nmov.b64 b, {%97, 0x40000040};\n"
               "wgmma.mma_async.sync.aligned.m64n192k16.f32.bf16.bf16 " R_ ", a, b, p, 1, 1, 0, 1;\nadd.s64 a, a, 2;\nadd.s64 b, b, 128;\n"
               "wgmma.mma_async.sync.aligned.m64n192k16.f32.bf16.bf16 " R_ ", a, b, q, 1, 1, 0, 1;\nadd.s64 a, a, 2;\nadd.s64 b, b, 128;\n"
               "wgmma.mma_async.sync.aligned.m64n192k16.f32.bf16.bf16 " R_ ", a, b, q, 1, 1, 0, 1;\nadd.s64 a, a, 2;\nadd.s64 b, b, 128;\n"
               "wgmma.mma_async.sync.aligned.m64n192k16.f32.bf16.bf16 " R_ ", a, b, q, 1, 1, 0, 1;\n}\n"
               : "+f"(d[0]), "+f"(d[1]), "+f"(d[2]), "+f"(d[3]), "+f"(d[4]), "+f"(d[5]), "+f"(d[6]), "+f"(d[7]), "+f"(d[8]), "+f"(d[9]), "+f"(d[10]), "+f"(d[11]), "+f"(d[12]), "+f"(d[13]), "+f"(d[14]), "+f"(d[15]), "+f"(d[16]), "+f"(d[17]), "+f"(d[18]), "+f"(d[19]), "+f"(d[20]), "+f"(d[21]), "+f"(d[22]), "+f"(d[23]), "+f"(d[24]), "+f"(d[25]), "+f"(d[26]), "+f"(d[27]), "+f"(d[28]), "+f"(d[29]), "+f"(d[30]), "+f"(d[31]), "+f"(d[32]), "+f"(d[33]), "+f"(d[34]), "+f"(d[35]), "+f"(d[36]), "+f"(d[37]), "+f"(d[38]), "+f"(d[39]), "+f"(d[40]), "+f"(d[41]), "+f"(d[42]), "+f"(d[43]), "+f"(d[44]), "+f"(d[45]), "+f"(d[46]), "+f"(d[47]), "+f"(d[48]), "+f"(d[49]), "+f"(d[50]), "+f"(d[51]), "+f"(d[52]), "+f"(d[53]), "+f"(d[54]), "+f"(d[55]), "+f"(d[56]), "+f"(d[57]), "+f"(d[58]), "+f"(d[59]), "+f"(d[60]), "+f"(d[61]), "+f"(d[62]), "+f"(d[63]), "+f"(d[64]), "+f"(d[65]), "+f"(d[66]), "+f"(d[67]), "+f"(d[68]), "+f"(d[69]), "+f"(d[70]), "+f"(d[71]), "+f"(d[72]), "+f"(d[73]), "+f"(d[74]), "+f"(d[75]), "+f"(d[76]), "+f"(d[77]), "+f"(d[78]), "+f"(d[79]), "+f"(d[80]), "+f"(d[81]), "+f"(d[82]), "+f"(d[83]), "+f"(d[84]), "+f"(d[85]), "+f"(d[86]), "+f"(d[87]), "+f"(d[88]), "+f"(d[89]), "+f"(d[90]), "+f"(d[91]), "+f"(d[92]), "+f"(d[93]), "+f"(d[94]), "+f"(d[95])
               : "r"(da), "r"(db), "n"(scale_d));
#undef R_
}
template <int scale_d> __device__ __forceinline__ void wgmma4_n128(float* d, uint32_t da, uint32_t db) {
#define R_ "{%0,%1,%2,%3,%4,%5,%6,%7,%8,%9,%10,%11,%12,%13,%14,%15,%16,%17,%18,%19,%20,%21,%22,%23,%24,%25,%26,%27,%28,%29,%30,%31,%32,%33,%34,%35,%36,%37,%38,%39,%40,%41,%42,%43,%44,%45,%46,%47,%48,%49,%50,%51,%52,%53,%54,%55,%56,%57,%58,%59,%60,%61,%62,%63}"
  asm volatile("{\n.reg .pred p, q;\n.reg .b64 a, b;\nsetp.ne.b32 p, %66, 0;\nsetp.eq.b32 q, 0, 0;\nmov.b64 a, {%64, 0x40000040};\nmov.b64 b, {%65, 0x40000040};\n"
               "wgmma.mma_async.sync.aligned.m64n128k16.f32.bf16.bf16 " R_ ", a, b, p, 1, 1, 0, 1;\nadd.s64 a, a, 2;\nadd.s64 b, b, 128;\n"
               "wgmma.mma_async.sync.aligned.m64n128k16.f32.bf16.bf16 " R_ ", a, b, q, 1, 1, 0, 1;\nadd.s64 a, a, 2;\nadd.s64 b, b, 128;\n"
               "wgmma.mma_async.sync.aligned.m64n128k16.f32.bf16.bf16 " R_ ", a, b, q, 1, 1, 0, 1;\nadd.s64 a, a, 2;\nadd.s64 b, b, 128;\n"
               "wgmma.mma_async.sync.aligned.m64n128k16.f32.bf16.bf16 " R_ ", a, b, q, 1, 1, 0, 1;\n}\n"
               : "+f"(d[0]), "+f"(d[1]), "+f"(d[2]), "+f"(d[3]), "+f"(d[4]), "+f"(d[5]), "+f"(d[6]), "+f"(d[7]), "+f"(d[8]), "+f"(d[9]), "+f"(d[10]), "+f"(d[11]), "+f"(d[12]), "+f"(d[13]), "+f"(d[14]), "+f"(d[15]), "+f"(d[16]), "+f"(d[17]), "+f"(d[18]), "+f"(d[19]), "+f"(d[20]), "+f"(d[21]), "+f"(d[22]), "+f"(d[23]), "+f"(d[24]), "+f"(d[25]), "+f"(d[26]), "+f"(d[27]), "+f"(d[28]), "+f"(d[29]), "+f"(d[30]), "+f"(d[31]), "+f"(d[32]), "+f"(d[33]), "+f"(d[34]), "+f"(d[35]), "+f"(d[36]), "+f"(d[37]), "+f"(d[38]), "+f"(d[39]), "+f"(d[40]), "+f"(d[41]), "+f"(d[42]), "+f"(d[43]), "+f"(d[44]), "+f"(d[45]), "+f"(d[46]), "+f"(d[47]), "+f"(d[48]), "+f"(d[49]), "+f"(d[50]), "+f"(d[51]), "+f"(d[52]), "+f"(d[53]), "+f"(d[54]), "+f"(d[55]), "+f"(d[56]), "+f"(d[57]), "+f"(d[58]), "+f"(d[59]), "+f"(d[60]), "+f"(d[61]), "+f"(d[62]), "+f"(d[63])
               : "r"(da), "r"(db), "n"(scale_d));
#undef R_
}
template <int scale_d> __device__ __forceinline__ void wgmma_n32(float* d, uint64_t descA, uint64_t descB) {
  asm volatile("{\n.reg .pred p;\nsetp.ne.b32 p, %18, 0;\n"
               "wgmma.mma_async.sync.aligned.m64n32k16.f32.bf16.bf16 {%0,%1,%2,%3,%4,%5,%6,%7,%8,%9,%10,%11,%12,%13,%14,%15}, %16, %17, p, 1, 1, 0, 1;\n}\n"
               : "+f"(d[0]), "+f"(d[1]), "+f"(d[2]), "+f"(d[3]), "+f"(d[4]), "+f"(d[5]), "+f"(d[6]), "+f"(d[7]), "+f"(d[8]), "+f"(d[9]), "+f"(d[10]), "+f"(d[11]), "+f"(d[12]), "+f"(d[13]), "+f"(d[14]), "+f"(d[15])
               : "l"(descA), "l"(descB), "n"(scale_d));
}
template <int scale_d, int tnsp_a> __device__ __forceinline__ void wgmma_n40(float* d, uint64_t descA, uint64_t descB) {
  asm volatile("{\n.reg .pred p;\nsetp.ne.b32 p, %22, 0;\n"
               "wgmma.mma_async.sync.aligned.m64n40k16.f32.bf16.bf16 {%0,%1,%2,%3,%4,%5,%6,%7,%8,%9,%10,%11,%12,%13,%14,%15,%16,%17,%18,%19}, %20, %21, p, 1, 1, %23, 1;\n}\n"
               : "+f"(d[0]), "+f"(d[1]), "+f"(d[2]), "+f"(d[3]), "+f"(d[4]), "+f"(d[5]), "+f"(d[6]), "+f"(d[7]), "+f"(d[8]), "+f"(d[9]), "+f"(d[10]), "+f"(d[11]), "+f"(d[12]), "+f"(d[13]), "+f"(d[14]), "+f"(d[15]), "+f"(d[16]), "+f"(d[17]), "+f"(d[18]), "+f"(d[19])
               : "l"(descA), "l"(descB), "n"(scale_d), "n"(tnsp_a));
}
template <int scale_d> __device__ __forceinline__ void wgmma_n40_rs(float* d, const uint32_t* a, uint64_t descB) {
  asm volatile("{\n.reg .pred p;\nsetp.ne.b32 p, %25, 0;\n"
               "wgmma.mma_async.sync.aligned.m64n40k16.f32.bf16.bf16 {%0,%1,%2,%3,%4,%5,%6,%7,%8,%9,%10,%11,%12,%13,%14,%15,%16,%17,%18,%19}, {%20,%21,%22,%23}, %24, p, 1, 1, 1;\n}\n"
               : "+f"(d[0]), "+f"(d[1]), "+f"(d[2]), "+f"(d[3]), "+f"(d[4]), "+f"(d[5]), "+f"(d[6]), "+f"(d[7]), "+f"(d[8]), "+f"(d[9]), "+f"(d[10]), "+f"(d[11]), "+f"(d[12]), "+f"(d[13]), "+f"(d[14]), "+f"(d[15]), "+f"(d[16]), "+f"(d[17]), "+f"(d[18]), "+f"(d[19])
               : "r"(a[0]), "r"(a[1]), "r"(a[2]), "r"(a[3]), "l"(descB), "n"(scale_d));
}
__device__ __forceinline__ void wgmma_copy(float* d, uint32_t da, uint64_t descB, int keep) {
  asm volatile("{\n.reg .pred p;\n.reg .b64 a;\nsetp.ne.b32 p, %66, 0;\nmov.b64 a, {%64, 0x40000040};\n"
               "wgmma.mma_async.sync.aligned.m64n16k16.f32.bf16.bf16 {%0,%1,%2,%3,%4,%5,%6,%7}, a, %65, p, 1, 1, 0, 0;\nadd.s64 a, a, 2;\n"
               "wgmma.mma_async.sync.aligned.m64n16k16.f32.bf16.bf16 {%8,%9,%10,%11,%12,%13,%14,%15}, a, %65, p, 1, 1, 0, 0;\nadd.s64 a, a, 2;\n"
               "wgmma.mma_async.sync.aligned.m64n16k16.f32.bf16.bf16 {%16,%17,%18,%19,%20,%21,%22,%23}, a, %65, p, 1, 1, 0, 0;\nadd.s64 a, a, 2;\n"
               "wgmma.mma_async.sync.aligned.m64n16k16.f32.bf16.bf16 {%24,%25,%26,%27,%28,%29,%30,%31}, a, %65, p, 1, 1, 0, 0;\nadd.s64 a, a, 1018;\n"
               "wgmma.mma_async.sync.aligned.m64n16k16.f32.bf16.bf16 {%32,%33,%34,%35,%36,%37,%38,%39}, a, %65, p, 1, 1, 0, 0;\nadd.s64 a, a, 2;\n"
               "wgmma.mma_async.sync.aligned.m64n16k16.f32.bf16.bf16 {%40,%41,%42,%43,%44,%45,%46,%47}, a, %65, p, 1, 1, 0, 0;\nadd.s64 a, a, 2;\n"
               "wgmma.mma_async.sync.aligned.m64n16k16.f32.bf16.bf16 {%48,%49,%50,%51,%52,%53,%54,%55}, a, %65, p, 1, 1, 0, 0;\nadd.s64 a, a, 2;\n"
               "wgmma.mma_async.sync.aligned.m64n16k16.f32.bf16.bf16 {%56,%57,%58,%59,%60,%61,%62,%63}, a, %65, p, 1, 1, 0, 0;\n"
               "}\n"
               : "+f"(d[0]), "+f"(d[1]), "+f"(d[2]), "+f"(d[3]), "+f"(d[4]), "+f"(d[5]), "+f"(d[6]), "+f"(d[7]), "+f"(d[8]), "+f"(d[9]), "+f"(d[10]), "+f"(d[11]), "+f"(d[12]), "+f"(d[13]), "+f"(d[14]), "+f"(d[15]), "+f"(d[16]), "+f"(d[17]), "+f"(d[18]), "+f"(d[19]), "+f"(d[20]), "+f"(d[21]), "+f"(d[22]), "+f"(d[23]), "+f"(d[24]), "+f"(d[25]), "+f"(d[26]), "+f"(d[27]), "+f"(d[28]), "+f"(d[29]), "+f"(d[30]), "+f"(d[31]), "+f"(d[32]), "+f"(d[33]), "+f"(d[34]), "+f"(d[35]), "+f"(d[36]), "+f"(d[37]), "+f"(d[38]), "+f"(d[39]), "+f"(d[40]), "+f"(d[41]), "+f"(d[42]), "+f"(d[43]), "+f"(d[44]), "+f"(d[45]), "+f"(d[46]), "+f"(d[47]), "+f"(d[48]), "+f"(d[49]), "+f"(d[50]), "+f"(d[51]), "+f"(d[52]), "+f"(d[53]), "+f"(d[54]), "+f"(d[55]), "+f"(d[56]), "+f"(d[57]), "+f"(d[58]), "+f"(d[59]), "+f"(d[60]), "+f"(d[61]), "+f"(d[62]), "+f"(d[63])
               : "r"(da), "l"(descB), "r"(keep));
}
__device__ __forceinline__ uint64_t make_desc(uint32_t addr, uint32_t lbo_bytes, uint32_t sbo_bytes) {
  return (uint64_t)((addr & 0x3FFFF) >> 4) | ((uint64_t)(lbo_bytes >> 4) << 16) | ((uint64_t)(sbo_bytes >> 4) << 32) | (1ull << 62);
}

__device__ __forceinline__ void ldsm_x4(uint32_t addr, uint32_t& r0, uint32_t& r1, uint32_t& r2, uint32_t& r3) {
  asm volatile("ldmatrix.sync.aligned.m8n8.x4.shared.b16 {%0,%1,%2,%3}, [%4];" : "=r"(r0), "=r"(r1), "=r"(r2), "=r"(r3) : "r"(addr) : "memory");
}
__device__ __forceinline__ void ldsm_x4_t(uint32_t addr, uint32_t& r0, uint32_t& r1, uint32_t& r2, uint32_t& r3) {
  asm volatile("ldmatrix.sync.aligned.m8n8.x4.trans.shared.b16 {%0,%1,%2,%3}, [%4];" : "=r"(r0), "=r"(r1), "=r"(r2), "=r"(r3) : "r"(addr) : "memory");
}
__device__ __forceinline__ void stsm_x4(uint32_t addr, uint32_t r0, uint32_t r1, uint32_t r2, uint32_t r3) {
  asm volatile("stmatrix.sync.aligned.m8n8.x4.shared.b16 [%0], {%1,%2,%3,%4};" :: "r"(addr), "r"(r0), "r"(r1), "r"(r2), "r"(r3) : "memory");
}
__device__ __forceinline__ void sts128(uint32_t addr, uint32_t a, uint32_t b, uint32_t c, uint32_t d) {
  asm volatile("st.shared.v4.u32 [%0], {%1,%2,%3,%4};" :: "r"(addr), "r"(a), "r"(b), "r"(c), "r"(d) : "memory");
}
__device__ __forceinline__ float lds32f(uint32_t addr) {
  float v;
  asm volatile("ld.shared.f32 %0, [%1];" : "=f"(v) : "r"(addr) : "memory");
  return v;
}
__device__ __forceinline__ void sts32f(uint32_t addr, float a) {
  asm volatile("st.shared.f32 [%0], %1;" :: "r"(addr), "f"(a) : "memory");
}
__device__ __forceinline__ void mma_bf16(float (&c)[4], uint32_t a0, uint32_t a1, uint32_t a2, uint32_t a3, uint32_t b0, uint32_t b1) {
  asm volatile("mma.sync.aligned.m16n8k16.row.col.f32.bf16.bf16.f32 {%0,%1,%2,%3}, {%4,%5,%6,%7}, {%8,%9}, {%0,%1,%2,%3};"
               : "+f"(c[0]), "+f"(c[1]), "+f"(c[2]), "+f"(c[3]) : "r"(a0), "r"(a1), "r"(a2), "r"(a3), "r"(b0), "r"(b1));
}
__device__ __forceinline__ void mma_bf16_z(float (&c)[4], uint32_t a0, uint32_t a1, uint32_t a2, uint32_t a3, uint32_t b0, uint32_t b1) {
  asm volatile("mma.sync.aligned.m16n8k16.row.col.f32.bf16.bf16.f32 {%0,%1,%2,%3}, {%4,%5,%6,%7}, {%8,%9}, {%10,%10,%10,%10};"
               : "=f"(c[0]), "=f"(c[1]), "=f"(c[2]), "=f"(c[3]) : "r"(a0), "r"(a1), "r"(a2), "r"(a3), "r"(b0), "r"(b1), "f"(0.f));
}
__device__ __forceinline__ uint32_t movm_t(uint32_t v) {
  uint32_t r;
  asm volatile("movmatrix.sync.aligned.m8n8.trans.b16 %0, %1;" : "=r"(r) : "r"(v));
  return r;
}
__device__ __forceinline__ uint32_t pack_bf16(float lo, float hi) {
  uint32_t r;
  asm("cvt.rn.bf16x2.f32 %0, %1, %2;" : "=r"(r) : "f"(hi), "f"(lo));
  return r;
}
__device__ __forceinline__ float bf_lo(uint32_t v) { return __uint_as_float(v << 16); }
__device__ __forceinline__ float bf_hi(uint32_t v) { return __uint_as_float(v & 0xFFFF0000u); }
__device__ __forceinline__ void split3(float x, uint32_t& h, uint32_t& m, uint32_t& l) {
  h = pack_bf16(x, 0.f); x -= bf_lo(h);
  m = pack_bf16(x, 0.f); x -= bf_lo(m);
  l = pack_bf16(x, 0.f);
}
__device__ __forceinline__ float ex2(float x) { float r; asm("ex2.approx.ftz.f32 %0, %1;" : "=f"(r) : "f"(x)); return r; }
__device__ __forceinline__ float rcp_fast(float x) { float r; asm("rcp.approx.ftz.f32 %0, %1;" : "=f"(r) : "f"(x)); return r; }
__device__ __forceinline__ void red_v4(float* p, float a, float b, float c, float d) {
  asm volatile("red.global.add.v4.f32 [%0], {%1, %2, %3, %4};" :: "l"(p), "f"(a), "f"(b), "f"(c), "f"(d) : "memory");
}
__device__ __forceinline__ uint4 ld_ll(const uint4* p) {
  uint4 v;
  asm volatile("{\n.reg .b64 a, b;\nld.relaxed.gpu.global.v2.b64 {a, b}, [%4];\nmov.b64 {%0, %1}, a;\nmov.b64 {%2, %3}, b;\n}\n"
               : "=r"(v.x), "=r"(v.y), "=r"(v.z), "=r"(v.w) : "l"(p) : "memory");
  return v;
}
__device__ __forceinline__ void st_b64(uint2* p, uint32_t a, uint32_t b) {
  asm volatile("{\n.reg .b64 v;\nmov.b64 v, {%1, %2};\nst.relaxed.gpu.global.b64 [%0], v;\n}\n" :: "l"(p), "r"(a), "r"(b) : "memory");
}
__device__ __forceinline__ void st_b128(uint4* p, uint32_t a, uint32_t b, uint32_t c, uint32_t d) {
  asm volatile("{\n.reg .b128 v;\nmov.b128 v, {%1, %2, %3, %4};\nst.relaxed.gpu.global.b128 [%0], v;\n}\n" :: "l"(p), "r"(a), "r"(b), "r"(c), "r"(d) : "memory");
}
__device__ __forceinline__ uint4 ld_b128(const uint4* p) {
  uint4 v;
  asm volatile("{\n.reg .b128 v;\nld.relaxed.gpu.global.b128 v, [%4];\nmov.b128 {%0, %1, %2, %3}, v;\n}\n" : "=r"(v.x), "=r"(v.y), "=r"(v.z), "=r"(v.w) : "l"(p) : "memory");
  return v;
}

constexpr float LOG2E = 1.4426950408889634f;

struct Params {
  const __nv_bfloat16* x0;
  const __nv_bfloat16* wA_qkv;
  const __nv_bfloat16* wA_o;
  const __nv_bfloat16* wB_qkv;
  const __nv_bfloat16* wB_phi;
  const __nv_bfloat16* wB_o;
  __nv_bfloat16* out;
};

#define ACC_DEF(d, n) _Pragma("unroll") for (int i_ = 0; i_ < (n); i_++) asm volatile("" : "=f"(d[i_]))
#define ACC_FENCE(d, n) _Pragma("unroll") for (int i_ = 0; i_ < (n); i_++) asm volatile("" : "+f"(d[i_]) :: "memory")
#define PIN(a, n) _Pragma("unroll") for (int i_ = 0; i_ < (n); i_++) asm volatile("" : "+f"((a)[i_]))
#define PINU(a, n) _Pragma("unroll") for (int i_ = 0; i_ < (n); i_++) asm volatile("" : "+r"((a)[i_]))

#define V_ADDR(p0) uint32_t va_[2] = {(p0) + (srowoff >> 1) + (lhi ^ lsw2), (p0) + (srowoff >> 1) + ((32 + lhi) ^ lsw2)}
#define STAGE_V(acc) { \
    _Pragma("unroll") for (int j_ = 0; j_ < 4; j_++) { \
      const float* a_ = (acc) + j_ * 8; \
      stsm_x4(va_[j_ & 1] + (j_ >> 1) * 8192, \
              pack_bf16(rs0 * a_[0], rs0 * a_[1]), pack_bf16(rs1 * a_[2], rs1 * a_[3]), pack_bf16(rs0 * a_[4], rs0 * a_[5]), pack_bf16(rs1 * a_[6], rs1 * a_[7])); } }
#define FRAG(dst, acc, TR, grp) { \
    _Pragma("unroll") for (int i_ = 0; i_ < 16; i_++) { \
      const float r_ = (i_ & 1) ? rs1 : rs0; \
      const uint32_t w_ = pack_bf16(r_ * (acc)[2 * i_], r_ * (acc)[2 * i_ + 1]); \
      if (TR) (dst)[i_] = movm_t(w_); else (dst)[(i_ & 12) + (i_ & 1) * 2 + ((i_ >> 1) & 1)] = w_; } \
    if (warp == 7 && mm < 15) { \
      _Pragma("unroll") for (int j_ = 0; j_ < 4; j_++) \
        st_b128(g_halo + (size_t)(mm * 8 + jj) * 512 + ((grp) * 4 + j_) * 32 + lane, ((dst)[j_ * 4] & ~1u) | H_BIT(l), (dst)[j_ * 4 + 1], (dst)[j_ * 4 + 2], (dst)[j_ * 4 + 3]); } \
    PINU(dst, 16); }
#define FRAG_PUT(src, slot) if (warp < 7) { _Pragma("unroll") for (int j_ = 0; j_ < 4; j_++) \
      sts128(sbase + (slot) * SLOT + 2048 + warp * 2048 + j_ * 512 + lane * 16, (src)[j_ * 4], (src)[j_ * 4 + 1], (src)[j_ * 4 + 2], (src)[j_ * 4 + 3]); }
#define FRAG_GET(dst, slot) { _Pragma("unroll") for (int j_ = 0; j_ < 4; j_++) \
      asm volatile("ld.shared.v4.u32 {%0, %1, %2, %3}, [%4];" : "=r"((dst)[j_ * 4]), "=r"((dst)[j_ * 4 + 1]), "=r"((dst)[j_ * 4 + 2]), "=r"((dst)[j_ * 4 + 3]) \
                   : "r"(sbase + (slot) * SLOT + warp * 2048 + j_ * 512 + lane * 16) : "memory"); }
#define RW(j) (((j) >> 1) * 4 + ((j) & 1))
template <int POS> __device__ __forceinline__ float exps16_(float* o, const float* p) {
  float s[4];
#pragma unroll
  for (int j = 0; j < 16; j++) { o[j] = ex2(POS ? p[RW(j)] : -p[RW(j)]); if (j < 4) s[j] = o[j]; else s[j & 3] += o[j]; }
  const float r = (s[0] + s[1]) + (s[2] + s[3]);
  return r + __shfl_xor_sync(0xffffffffu, r, 1);
}
template <int POS> __device__ __forceinline__ void exps16_fix(float* o, const float* p, float& sum) {
  if (__builtin_expect(__any_sync(0xffffffffu, !(sum > SUMLO && sum < SUMHI)), 0)) {
    float m = p[0], q[32];
#pragma unroll
    for (int j = 1; j < 16; j++) m = POS ? fmaxf(m, p[RW(j)]) : fminf(m, p[RW(j)]);
    const float x = __shfl_xor_sync(0xffffffffu, m, 1);
    m = POS ? fmaxf(m, x) : fminf(m, x);
#pragma unroll
    for (int j = 0; j < 16; j++) q[RW(j)] = p[RW(j)] - m;
    sum = exps16_<POS>(o, q);
  }
}
__device__ __forceinline__ void store16(const float* e, float sum, uint32_t dst, uint32_t dsw, int c0) {
  const float inv = rcp_fast(sum);
#pragma unroll
  for (int j = 0; j < 2; j++)
    sts128(dst + (((c0 + j) << 4) ^ dsw), pack_bf16(e[j * 8] * inv, e[j * 8 + 1] * inv), pack_bf16(e[j * 8 + 2] * inv, e[j * 8 + 3] * inv),
           pack_bf16(e[j * 8 + 4] * inv, e[j * 8 + 5] * inv), pack_bf16(e[j * 8 + 6] * inv, e[j * 8 + 7] * inv));
}
template <int POS> __device__ __forceinline__ void expp16(uint32_t* o, float* p) {
  {
#pragma unroll
    for (int r = 0; r < 4; r += 2) {
      float m = p[r];
#pragma unroll
      for (int j = 1; j < 8; j++) m = POS ? fmaxf(m, p[r + RW(j)]) : fminf(m, p[r + RW(j)]);
#pragma unroll
      for (int s = 1; s <= 2; s <<= 1) { const float x = __shfl_xor_sync(0xffffffffu, m, s); m = POS ? fmaxf(m, x) : fminf(m, x); }
#pragma unroll
      for (int j = 0; j < 8; j++) p[r + RW(j)] -= m;
    }
  }
#pragma unroll
  for (int j = 0; j < 8; j++) o[j] = pack_bf16(ex2(POS ? p[2 * j] : -p[2 * j]), ex2(POS ? p[2 * j + 1] : -p[2 * j + 1]));
}
__device__ __forceinline__ void scale32(float* o, const float* p, float c0, float c1) {
#pragma unroll
  for (int i = 0; i < 32; i++) asm volatile("mul.f32 %0, %1, %2;" : "=f"(o[i]) : "f"(p[i]), "f"((i & 2) ? c1 : c0));
}
__device__ __forceinline__ bool any_big(const float* p) {
  float m[4];
#pragma unroll
  for (int i = 0; i < 32; i++) m[i >> 3] = (i & 7) ? fmaf(p[i], p[i], m[i >> 3]) : p[i] * p[i];
  return __any_sync(0xffffffffu, !(fmaxf(fmaxf(m[0], m[1]), fmaxf(m[2], m[3])) < BIGLIM));
}
__device__ __forceinline__ void phiq_a(float* p, bool big) {
  if (__builtin_expect(!big, 1)) {
#pragma unroll
    for (int j = 0; j < 16; j++) p[j] = ex2(p[j]);
  }
}
template <int NEXT> __device__ __forceinline__ void phiq_b(uint32_t* o, float* p, bool big) {
  if (__builtin_expect(big, 0)) {
    expp16<0>(o, p); expp16<1>(o + 8, p);
  } else {
    if (NEXT) phiq_a(p + 16, false);
#pragma unroll
    for (int j = 0; j < 4; j++) {
      const float a = p[4 * j], b = p[4 * j + 1], c = p[4 * j + 2], d = p[4 * j + 3];
      const float ab = a * b, cd = c * d, r = rcp_fast(ab * cd), x = r * cd, y = r * ab;
      o[2 * j] = pack_bf16(x * b, x * a); o[2 * j + 1] = pack_bf16(y * d, y * c);
      o[8 + 2 * j] = pack_bf16(a, b); o[9 + 2 * j] = pack_bf16(c, d);
    }
  }
}
#define SCHED_FENCE() asm volatile("pmevent 0;" ::: "memory")

__global__ void __cluster_dims__(2, 1, 1) __launch_bounds__(384, 1)
mega_kernel(const __grid_constant__ CUtensorMap tm_x0, const __grid_constant__ CUtensorMap tm_xo, const __grid_constant__ CUtensorMap tm_os,
            const __grid_constant__ CUtensorMap tm_o, const __grid_constant__ CUtensorMap tm_wf,
            const __grid_constant__ CUtensorMap tm_wqA, const __grid_constant__ CUtensorMap tm_wqB,
            const __grid_constant__ CUtensorMap tm_woA, const __grid_constant__ CUtensorMap tm_woB,
            const __grid_constant__ CUtensorMap tm_phi, const Params prm) {
  extern __shared__ __align__(1024) uint8_t smem_raw[];
  const uint32_t sbase = smem_u32(smem_raw);
  const uint32_t bar_full = sbase + OFF_BAR;
  const uint32_t bar_done = bar_full + 384;
  const uint32_t bar_stat = bar_full + 768, bar_stat2 = bar_full + 776, bar_epi = bar_full + 784, bar_phi = bar_full + 936  , bar_halo = bar_full + 904  ;
  const uint32_t bar_xr = bar_full + 800, bar_lx = bar_full + 808, bar_stg = bar_full + 832;
  const uint32_t bar_chk = bar_full + 848;

  const int warp = __shfl_sync(0xffffffffu, threadIdx.x >> 5, 0), lane = threadIdx.x & 31;
  uint32_t rank;
  asm volatile("mov.u32 %0, %%cluster_ctarank;" : "=r"(rank));
  const int aux = (int)blockIdx.x - NMAIN, tp = (int)(blockIdx.x >> 1) - 4;
  const int gp = tp < 0 ? 0 : (tp < 32 ? tp & 7 : 1 + (tp - 32) % 7), me = tp < 0 ? tp + 8 : (tp < 32 ? tp >> 3 : 4 + (tp - 32) / 7);
  const int jj = me, cc = gp;
  const int cta = aux >= 0 ? -1 : (cc * 8 + jj) * 2 + (int)rank;
  const int mm = cc * 2 + (int)rank;

#define LOAD_EPOCH() const unsigned epoch = ld_relaxed(&g_flags.epoch.v), ep1 = epoch + 1; (void)epoch
  int budget = 1 << 22;

  if (cta >= 0) {
    if (warp >= 8 && warp < 8 + EARLY && elect_one()) {
      const int u = warp - 8;
      const uint32_t fb = bar_full + u * 8;
      mbar_init(fb, 1);
      asm volatile("fence.mbarrier_init.release.cluster;" ::: "memory");
      fence_proxy_async_smem();
      mbar_expect_tx(fb, u < 2 ? QST + SLOT : QST);
      if (u && STAG2) __nanosleep(STAG2);
      if (u < 2) tma_load_2d(sbase + OFF_S + u * SLOT, &tm_x0, fb, jj * 128 + u * 64, mm * 128);
#pragma unroll
      for (int i = 0; i < 6; i++) tma_load_2d(sbase + u * QST + i * 4096, &tm_wqA, fb, jj * 128 + (u >> 1) * 64 + (i >> 1) * 1024, jj * 128 + (u & 1) * 64 + (i & 1) * 32);
      if (u == 0) PROFT(472);
    }
    __syncwarp();
    {
      const int tx = threadIdx.x;
      const __nv_bfloat16* pf = (tx < 128) ? prm.x0 + (size_t)(mm * 128 + tx) * D_MODEL + jj * 128
                                           : prm.wA_qkv + (size_t)(jj * 128 + (tx & 63)) * 3072 + ((tx - 128) >> 6) * 1024 + jj * 128 + rank * 64;
      if (tx < 320) { if (PF0) asm volatile("prefetch.global.L2 [%0];" :: "l"(pf)); }
      else if (tx == 320) prefetch_tmap(&tm_x0);
      else if (tx == 352) prefetch_tmap(&tm_wqA);
      else if (tx == 383) asm volatile("prefetch.global.L2 [%0];" :: "l"(&g_flags.epoch.v));
    }
    if (elect_one()) {
#pragma unroll
      for (int i = 0; i < 4; i++) {
        const int u = warp * 4 + i;
        if (u >= EARLY) mbar_init(bar_full + u * 8, ((u >= 4 && u < 11) || (u > 32 && u != 40)) ? 2 : 1); mbar_init(bar_done + u * 8, 16);
      }
      mbar_init(bar_stat + warp * 16, 0x111111181182ull >> (4 * warp) & 15);
      mbar_init(bar_stat + warp * 16 + 8, 0x111111121811ull >> (4 * warp) & 15);
      mbar_init(bar_chk + 112 + (warp & 7) * 8, 1);
      asm volatile("fence.mbarrier_init.release.cluster;" ::: "memory");
    }
    __syncthreads();
    asm volatile("barrier.cluster.arrive.relaxed.aligned;" ::: "memory");
  }

  if (cta < 0) {
    LOAD_EPOCH();
    const uint32_t buf = sbase + warp * SLOT, bar = sbase + OFF_BAR + warp * 16;
    const uint32_t lsw = (lane & 7) << 4, lhi = (lane >> 4) << 4, lrow = (lane & 15) * 128;
    const bool el = elect_one();
    if (el) {
      mbar_init(bar, 1); mbar_init(bar + 8, 1);
      asm volatile("fence.mbarrier_init.release.cluster;" ::: "memory");
    }
#pragma unroll 1
    for (int rd = 0; rd < (NLAYERS > 1 ? 5 : 2); rd++) {
      if (rd >= 2 && warp >= 8) break;
      const int tk = rd < 2 ? aux * 12 + warp : aux * 8 + warp;
      const int half = tk & 1;
      const int blk = rd < 2 ? (tk >> 1) * 2 + rd : (4 - rd) * 16 + (tk >> 1);
      const CUtensorMap* tm = rd < 2 ? &tm_wqA : (rd == 2 ? &tm_wqB : &tm_wf);
      const int j0 = (blk & 15) >> 1;
#define AUX_LOAD(n) { const uint32_t d_ = buf + ((n) & 1) * 8192, b_ = bar + ((n) & 1) * 8; const int r_ = kslice(j0, 2 * (n) + half) * 64; \
        mbar_expect_tx(b_, 8192); tma_load_2d(d_, tm, b_, blk * 64, r_); tma_load_2d(d_ + 4096, tm, b_, blk * 64, r_ + 32); }
      if (el) {
        if (rd == 3) { wait_flag(&g_flags.wfready[j0].v, ep1 * 16); fence_proxy_async_global(); }
        AUX_LOAD(0); AUX_LOAD(1);
      }
      __syncwarp();
      float cs[8][4];
#pragma unroll
      for (int i = 0; i < 8; i++) cs[i][0] = cs[i][1] = cs[i][2] = cs[i][3] = 0.f;
#pragma unroll 1
      for (int n = 0; n < 8; n++) {
        const uint32_t tb = buf + (n & 1) * 8192 + lrow;
        mbar_wait(bar + (n & 1) * 8, (n >> 1) & 1);
#pragma unroll
        for (int i = 0; i < 16; i++) {
          uint32_t b0, b1, b2, b3;
          ldsm_x4_t(tb + (i >> 2) * 2048 + (((i & 3) * 32 + lhi) ^ lsw), b0, b1, b2, b3);
          mma_bf16(cs[2 * (i & 3)], 0x3F803F80u, 0x3F803F80u, 0x3F803F80u, 0x3F803F80u, b0, b1);
          mma_bf16(cs[2 * (i & 3) + 1], 0x3F803F80u, 0x3F803F80u, 0x3F803F80u, 0x3F803F80u, b2, b3);
        }
        __syncwarp();
        if (el && n < 6) AUX_LOAD(n + 2);
        __syncwarp();
      }
      if (lane < 4) {
#pragma unroll
        for (int i = 0; i < 8; i++) st_b64(&g_colsum[rd >= 2][blk * 32 + i * 4 + lane][half], __float_as_uint(cs[i][0]), (__float_as_uint(cs[i][1]) & ~3u) | (ep1 & 3));
      }
      __syncwarp();
    }
  } else if (warp >= 8) {
    asm volatile("setmaxnreg.dec.sync.aligned.u32 40;");
    if (warp == 8) {
      const bool el = elect_one();
      cluster_wait();
      if (el) {
#pragma unroll 1
        for (int l = 0; l < NLAYERS; l++) {
          const uint32_t par = l & 1;
          const CUtensorMap* tqk = par ? &tm_wf : &tm_wqA;
          const CUtensorMap* tv = par ? &tm_wqB : &tm_wqA;
          const CUtensorMap* two = par ? &tm_woB : &tm_woA;
          if (l == 1) { LOAD_EPOCH(); wait_flag(&g_flags.wfready[jj].v, ep1 * 16); fence_proxy_async_global(); }
#pragma unroll 1
          for (int u = l ? 0 : EARLY; u < 32; u++) {
            if (u >= 4) mbar_wait_sl(bar_done + (u - 4) * 8, par);
            else if (l) mbar_wait_sl(bar_done + (43 + u + (u >> 1)) * 8, par ^ 1);
            else if (u == 1) __nanosleep(STAG1);
            else if (u == 2 && !W23) mbar_wait_sl(bar_full, 0);
            const uint32_t fb = bar_full + u * 8;
            const bool res = u < 4 ? (l || u >= 2) : (u < 11 || (u >= 18 && u < 22));
            mbar_expect_tx(fb, res ? QST : QST + SLOT);
            const int row = kslice(jj, u < 4 ? u & 1 : (u < 18 ? u - 2 : (u < 22 ? u - 6 : u - 20))) * 64 + (int)rank * 32;
            const int ps = u < 4 ? u >> 1 : (u >= 18), col = jj * 128 + ps * 64;
            const int c0 = par ? jj * 128 + (ps ? 0 : 1024) : col;
            const uint32_t dst = sbase + (u & 3) * QST + rank * 4096;
            tma_load_2d_mc(dst, tqk, fb, c0, row);
            tma_load_2d_mc(dst + 8192, tqk, fb, c0 + (par ? 64 : 1024), row);
            tma_load_2d_mc(dst + 16384, tv, fb, col + 2048, row);
            if (l == PRL && u >= PRU && u < PRU + 4) PROFT(473 + u - PRU);
          }
#pragma unroll 1
          for (int s = 0; s < 16; s++) {
            if (s < 5) { if (s != 2 && s != 4) mbar_wait_sl(bar_done + (28 + s) * 8, par); }
            else if (s != 14) mbar_wait_sl(bar_done + (27 + s - (s == 15)) * 8, par);
            const uint32_t fb = bar_full + (32 + s) * 8;
            mbar_expect_tx(fb, SLOT);
            tma_load_2d_mc(sbase + rank * 8192 + (uint32_t)((WO_BSLOT >> (4 * s)) & 15) * SLOT, two, fb, jj * 128 + (int)rank * 64, wslice(jj, s) * 64);
            const int ts = s + par;
            if (s >= 5 && ts < 8) {
              mbar_expect_tx(bar_chk - 8 + ts * 8, SLOT);
              tma_load_2d(sbase + (uint32_t)((WO_ASLOT(par) >> (4 * ts)) & 15) * SLOT, &tm_o, bar_chk - 8 + ts * 8, wslice(jj, ts) * 64, mm * 128);
            }
          }
        }
      }
      __syncwarp();
    } else if (warp == 9) {
      const bool el = elect_one();
      if (el) {
        if (!EARLY) { PROFT(472); tma_load_2d(sbase + OFF_S, &tm_x0, bar_full, jj * 128, mm * 128); }
        if (EARLY < 2) { __nanosleep(STAG1); tma_load_2d(sbase + OFF_S + SLOT, &tm_x0, bar_full + 8, jj * 128 + 64, mm * 128); }
      }
      __syncwarp();
      LOAD_EPOCH();
#pragma unroll 1
      for (int lp = 0; lp < 4 * NLAYERS; lp++) {
        const int l = lp >> 2, ph = lp & 3;
        if (ph == 3) continue;
        const uint32_t par = l & 1;
        const unsigned* pp = reinterpret_cast<const unsigned*>(g_obuf + (ph >> 1) * 64 + (size_t)(mm * 128 + (ph ? 0 : S_LEN) + (lane & 7) * 16 + (jj & 1) * 8) * D_MODEL +
                                                               (jj >> 1) * 16 + srcb(jj, lane >> 3) * 128);
        const CUtensorMap* tm = lp ? &tm_o : &tm_x0;
        const int row = mm * 128 + ((ph || !l) ? 0 : S_LEN);
        const uint32_t bit = ph ? O_BIT(l) : X_BIT(l - 1);
        const uint32_t slots = ph ? (uint32_t)(WO_ASLOT(par) >> (ph * 32 - 28)) : 0x8769876u;
        const unsigned long long fr = ph == 0 ? XPACE : ph == 1 ? (par ? 0x353535351Full : 0x35351F1Eull) : (par ? 0x27262524232232ull : 0x27262524233232ull);
        uint32_t no = (lp == 0 || (lp & 7) == 1) ? 0 : ~0u, v0 = 0, v1 = 0;
        if (lp || !AX) mbar_wait_sl(ph ? bar_done + ((uint32_t)fr & 63) * 8 : (l ? bar_done + 47 * 8 : bar_full), ph ? par : (l ? par ^ 1 : 0));
        if (el && ph) PROFT(324 + l * 16 + ph);
        __syncwarp();
        if (no) { v0 = ld_relaxed(pp); __nanosleep(POLLGAP); v1 = ld_relaxed(pp); }
#pragma unroll 1
        for (int i = 0; i < (ph == 1 ? 4 + par : 7); i++, no >>= 8) {
#pragma unroll 1
          for (int it = 0; (no & 0xFF) && it < (1 << 18); it++) {
            no &= __ballot_sync(0xffffffffu, (v0 ^ bit) & 1) >> (8 * i);
            if (no) v0 = ld_relaxed(pp);
            if (!(no & 0xFF)) break;
            no &= __ballot_sync(0xffffffffu, (v1 ^ bit) & 1) >> (8 * i);
            if (no) v1 = ld_relaxed(pp);
          }
          if (ph || i >= XP0) mbar_wait_sl(bar_done + ((uint32_t)(fr >> (8 * i)) & 63) * 8, par);
          if (el) {
            if (i == 0) PROFT(320 + l * 16 + ph);
            const uint32_t cb = bar_chk + (ph >> 1) * 112 + i * 8;
            mbar_expect_tx(cb, SLOT);
            tma_load_2d(sbase + ((slots >> (4 * i)) & 15) * SLOT, tm, cb, srcb(jj, i) * 128 + (ph >> 1) * 64, row);
          }
          __syncwarp();
        }
        if (ph == 0 && el) {
          if (l) { wait_flag(&g_flags.xready[l][mm].v, ep1 * 8); fence_proxy_async_global(); }
#pragma unroll 1
          for (int u = 11; u < 34; u++) {
            if (u == 18) u = 22;
            mbar_wait_sl(bar_done + (u - 4) * 8, par);
            if (u == 32) mbar_expect_tx(bar_xr, 2 * SLOT);
            tma_load_2d(sbase + OFF_RA + (u & 3) * SLOT, tm, u < 32 ? bar_full + u * 8 : bar_xr, kslice(jj, u < 18 ? u - 2 : (u < 32 ? u - 20 : u - 32)) * 64, row);
          }
        }
        __syncwarp();
      }
      if (el && atomicAdd(&g_flags.done.v, 1) == ep1 * NMAIN - 1) asm volatile("st.relaxed.gpu.global.u32 [%0], %1;" :: "l"(&g_flags.epoch.v), "r"(ep1) : "memory");
      __syncwarp();
      cluster_wait();
    } else {
      const int hw = warp - 10;
      LOAD_EPOCH();
      const bool el = elect_one();
      cluster_wait();
      if (hw == 0) {
        mbar_wait_sl(bar_full + 8, 0);
        if (lane < 7) prefetch_tmap(lane == 0 ? &tm_os : lane == 1 ? &tm_o : lane == 2 ? &tm_wf : lane == 3 ? &tm_wqB : lane == 4 ? &tm_woA : lane == 5 ? &tm_woB : &tm_phi);
#pragma unroll 1
        for (int i = 0; i < (NLAYERS > 1 ? 9 : 0); i++) {
          if (i == 0 || i == 5) mbar_wait_sl(bar_done + (i >> 1) * 12, 0);
          if (el) {
            if (i == 0) { mbar_expect_tx(bar_phi, 2 * SLOT + 8192); tma_load_2d(sbase + OFF_PHI, &tm_phi, bar_phi, 0, jj * 128); }
            else tma_load_2d(sbase + (i > 4 ? 10 : 12) * SLOT - 4096 + i * 4096, &tm_wqB, bar_phi, (i > 4 ? 896 : 0) + jj * 128 + ((i - 1) >> 1) * 64, mm * 64 + (~i & 1) * 32);
          }
          __syncwarp();
          __nanosleep(PFGAP);
        }
      } else {
        if (XMMA && lane < 24) {
          const uint32_t one = (lane & 8) ? 0u : 0x3F80u << ((lane & 1) * 16), w = (lane >> 1) & 3;
          sts128(sbase + OFF_ID + lane * 16, w == 0 ? one : 0u, w == 1 ? one : 0u, w == 2 ? one : 0u, w == 3 ? one : 0u);
        }
#pragma unroll 1
        for (int b = 0; b < 2; b++) {
          float4* z = reinterpret_cast<float4*>(g_kv[b] + (jj * 4) * KVH + mm * (4 * KVH / 16)) + lane;
#pragma unroll
          for (int i = 0; i < 6; i++) z[i * 32] = make_float4(0.f, 0.f, 0.f, 0.f);
        }
#pragma unroll 1
        for (int i = 0; i < 16; i++) {
          const int b = i >> 2;
          const uint32_t v = (b == 0 ? O_BIT(0) : b == 1 ? X_BIT(0) : H_BIT(0)) + 1;
          uint4* p = b < 2 ? reinterpret_cast<uint4*>(g_obuf + (size_t)(b * S_LEN + mm * 128 + (i & 3) * 32 + (lane >> 3) * 8) * D_MODEL + jj * 128 + (b ? 0 : 64)) + (lane & 7)
                           : g_halo + (size_t)(mm * 8 + jj) * 512 + i * 32 + lane;
          *p = make_uint4(v, v, v, v);
        }
        fence_proxy_async_global();
      }
      __syncwarp();
      uint32_t chkp = 0;
#pragma unroll 1
      for (int lp = 0; lp < 8 * NLAYERS; lp++) {
        const int l = lp >> 3, tk = lp & 7, ph = tk ? 2 - hw : 0;
        const uint32_t par = l & 1;
        int lane; asm volatile("mov.u32 %0, %%laneid;" : "=r"(lane));
        if (tk == 5 || (hw && tk == 0)) {
          const uint32_t bit = ph ? O_BIT(l) : X_BIT(l - 1);
          uint32_t slots = ph ? (uint32_t)(WO_ASLOT(par) >> (ph * 32 - 28)) : 0x8769876u;
          const uint32_t a0 = sbase + (lane & 7) * 126 + lane * 4 + (lane & 1) * 14;
#pragma unroll 1
          for (int c = 0; c < 7; c++, slots >>= 4) {
            const uint32_t cb = bar_chk + 112 - hw * 112 + c * 8;
#pragma unroll 1
            for (int it = 0; it < (1 << 12); it++) {
              mbar_wait_sl(cb, (chkp >> c) & 1);
              chkp ^= 1u << c;
              if (el && c == 0) PROFT(ph == 1 ? 480 + l * 2 : 488 + l * 2 + (ph >> 1));
              if (lp == 0) break;
              uint32_t bad;
              asm volatile("{\n.reg .b32 w<16>;\n"
                           "ld.shared.u32 w0, [%1 + 0];\n"
                           "ld.shared.u32 w1, [%1 + 1024];\n"
                           "ld.shared.u32 w2, [%1 + 2048];\n"
                           "ld.shared.u32 w3, [%1 + 3072];\n"
                           "ld.shared.u32 w4, [%1 + 4096];\n"
                           "ld.shared.u32 w5, [%1 + 5120];\n"
                           "ld.shared.u32 w6, [%1 + 6144];\n"
                           "ld.shared.u32 w7, [%1 + 7168];\n"
                           "ld.shared.u32 w8, [%1 + 8192];\n"
                           "ld.shared.u32 w9, [%1 + 9216];\n"
                           "ld.shared.u32 w10, [%1 + 10240];\n"
                           "ld.shared.u32 w11, [%1 + 11264];\n"
                           "ld.shared.u32 w12, [%1 + 12288];\n"
                           "ld.shared.u32 w13, [%1 + 13312];\n"
                           "ld.shared.u32 w14, [%1 + 14336];\n"
                           "ld.shared.u32 w15, [%1 + 15360];\n"
                           "lop3.b32 w0, w0, w1, %2, 0x7E;\n"
                           "lop3.b32 w2, w2, w3, %2, 0x7E;\n"
                           "lop3.b32 w4, w4, w5, %2, 0x7E;\n"
                           "lop3.b32 w6, w6, w7, %2, 0x7E;\n"
                           "lop3.b32 w8, w8, w9, %2, 0x7E;\n"
                           "lop3.b32 w10, w10, w11, %2, 0x7E;\n"
                           "lop3.b32 w12, w12, w13, %2, 0x7E;\n"
                           "lop3.b32 w14, w14, w15, %2, 0x7E;\n"
                           "lop3.b32 w0, w0, w2, w4, 0xFE;\nlop3.b32 w6, w6, w8, w10, 0xFE;\nlop3.b32 w0, w0, w12, w14, 0xFE;\nlop3.b32 %0, w0, w6, 1, 0xA8;\n}\n"
                           : "=r"(bad) : "r"(a0 + (slots & 15) * SLOT), "r"(bit) : "memory");
              if (__all_sync(0xffffffffu, bad == 0)) break;
              if (el) {
                fence_proxy_async_smem();
                mbar_expect_tx(cb, SLOT);
                tma_load_2d(sbase + (slots & 15) * SLOT, &tm_o, cb, srcb(jj, c) * 128 + (ph >> 1) * 64, mm * 128 + (ph ? 0 : S_LEN));
                RETRY_COUNT();
              }
              __syncwarp();
            }
            if (el) { mbar_arrive_local(bar_full + (c + (ph ? 25 + ph * 8 : 4)) * 8); if (lp == PRL * 8 && c == 0) PROFT(477); }
            __syncwarp();
          }
        } else if (hw && (tk & 5) == 1) {
          {
            const int hp = tk >> 1;
            const uint4* src = reinterpret_cast<const uint4*>(g_colsum[par][jj * 64 + hp * 32 + lane]);
            uint32_t bad;
            int it = 0;
            float c[6];
            do {
              bad = 0;
#pragma unroll
              for (int p = 0; p < 3; p++) {
                const uint4 v = ld_ll(src + ((par && p < 2) ? (hp ? -32 : 512) + p * 32 : p * 512));
                bad |= (v.y ^ ep1) | (v.w ^ ep1);
                c[2 * p] = __uint_as_float(v.x) + __uint_as_float(v.z); c[2 * p + 1] = __uint_as_float(v.y) + __uint_as_float(v.w);
              }
              bad &= 3;
              if (bad) __nanosleep(300);
            } while (bad && ++it < (1 << 16));
#pragma unroll
            for (int p = 0; p < 6; p++) {
              uint32_t h, m, lo;
              split3(c[p], h, m, lo);
              sts128(sbase + OFF_LNB + hp * 4096 + (p >> 1) * 1024 + lane * 32 + (p & 1) * 16, h | (m << 16), h | (lo << 16), h | (m << 16), lo | (m << 16));
            }
            fence_proxy_async_smem();
            __syncwarp();
            if (el) { mbar_arrive_local(hp ? bar_stat2 : bar_stat); if (hp == 0) PROFT(324 + l * 16); }
            __syncwarp();
          }
        } else if (tk == 0) {
          mbar_wait_sl(bar_done + 24, par);
          const uint4* sp = reinterpret_cast<const uint4*>(g_stats + (size_t)(mm * 128) * 8) + lane;
#pragma unroll 1
          for (int hf = 0; hf < 4; hf++) {
            uint4 v[4];
            uint32_t bad;
            int it = 0;
            do {
              bad = 0;
#pragma unroll
              for (int i = 0; i < 4; i++) { v[i] = ld_ll(sp + (hf * 4 + i) * 32); bad |= (v[i].y ^ STAT_TAG(l)) | (v[i].w ^ STAT_TAG(l)); }
              bad &= 3;
              if (bad) __nanosleep(200);
            } while (bad && ++it < (1 << 16));
            __syncwarp();
            float mean = 0.f, m2 = 0.f;
#pragma unroll
            for (int i = 0; i < 4; i++) {
              float a = __uint_as_float(v[i].x) + __uint_as_float(v[i].z);
              a += __shfl_xor_sync(0xffffffffu, a, 1); a += __shfl_xor_sync(0xffffffffu, a, 2);
              a *= 0.125f;
              const float e0 = __uint_as_float(v[i].x) - a, e1 = __uint_as_float(v[i].z) - a;
              float q = fmaf(fmaf(e0, e0, e1 * e1), 128.f, __uint_as_float(v[i].y) + __uint_as_float(v[i].w));
              q += __shfl_xor_sync(0xffffffffu, q, 1); q += __shfl_xor_sync(0xffffffffu, q, 2);
              if ((lane & 3) == i) { mean = a; m2 = q; }
            }
            const uint32_t row = hf * 32 + (lane & 3) * 8 + (lane >> 2);
            uint32_t h, m, lo;
            split3(-0.5f * mean, h, m, lo);
            sts128(sbase + OFF_LNA + row * 16, h | (h << 16), m | (h << 16), lo | (m << 16), m | (lo << 16));
            sts32f(sbase + OFF_ST + row * 4, rsqrtf(m2 * (1.f / 1024.f) + 1e-5f));
          }
          fence_proxy_async_smem();
          __syncwarp();
          if (el) { mbar_arrive_local(bar_stat); PROFT(323 + l * 16); }
          __syncwarp();
#pragma unroll 1
          for (int i = 0; i < 8 - 4 * l; i++) {
            asm volatile("prefetch.global.L2 [%0];" :: "l"(i < 4 ? (l ? prm.wB_o : prm.wA_o) + (size_t)cta * 8192 + i * 2048 + lane * 64
                                                                 : prm.wB_qkv + (size_t)(cta * 8 + (i - 4) * 2 + (lane >> 4)) * 3072 + 2048 + (lane & 15) * 64));
            __nanosleep(PFGAP);
          }
        } else if (lp == 3) {
#pragma unroll 1
          for (int c = 0; c < (NLAYERS > 1 ? 8 : 0); c++) {
            if (!(c & 3)) asm volatile("bar.sync %0, 288;" :: "r"(BAR_WF + (c >> 2)) : "memory");
            if (el) {
              tma_store_2d(&tm_wf, sbase + 11 * SLOT + c * 4096, (c < 4 ? 1024 : -128) + jj * 128 + (c >> 1) * 64, mm * 64 + (c & 1) * 32);
              if ((c & 3) == 3) {
                asm volatile("cp.async.bulk.commit_group;\ncp.async.bulk.wait_group.read 0;" ::: "memory");
                mbar_arrive_local(bar_phi + (c >> 2) * 8);
              } else __nanosleep(WFGAP);
            }
            __syncwarp();
          }
          if (el) { bulk_commit_wait(); signal_release(&g_flags.wfready[jj].v); PROFT(335); }
          __syncwarp();
        } else if (tk == 2 || tk == 4) {
          if (par) continue;
          const int i = tk >> 2;
          mbar_wait_sl(bar_done + (i ? HW1 : (hw ? 19 : HW0)) * 8, 0);
          const uint4* src = g_halo + (size_t)(mm * 8 + jj - 8) * 512 + i * 256 + hw * 128 + lane;
          uint4 v[4];
          int it = 0;
          bool ok;
          do {
#pragma unroll
            for (int j = 0; j < 4; j++) v[j] = mm ? ld_b128(src + j * 32) : make_uint4(H_BIT(l), 0, 0, 0);
            ok = __all_sync(0xffffffffu, (((v[0].x ^ H_BIT(l)) | (v[1].x ^ H_BIT(l)) | (v[2].x ^ H_BIT(l)) | (v[3].x ^ H_BIT(l))) & 1) == 0);
          } while (!ok && ++it < (1 << 16));
          if (lp + hw == 3 && NLAYERS > 1) mbar_wait_sl(bar_phi, 1);
#pragma unroll
          for (int j = 0; j < 4; j++) sts128(sbase + OFF_S + hw * SLOT + j * 512 + lane * 16, v[j].x, v[j].y, v[j].z, v[j].w);
          __syncwarp();
          if (el) { mbar_arrive_local(bar_halo + hw * 8); PROFT(331 + l * 16 + i * 2 + hw); }
          __syncwarp();
        } else if (tk == 6 && hw == 0 && l < NLAYERS - 1) {
          bar_sync<BAR_X1, 288>();
          if (el) {
            PROFT(328 + l * 16);
            mbar_wait_sl(bar_full + XD * 8, par ^ 1);
            tma_store_2d(&tm_o, sbase + 11 * SLOT, jj * 128 + 64, mm * 128 + S_LEN);
            bulk_commit_wait();
            signal_release(&g_flags.xready[l + 1][mm].v);
            PROFT(330 + l * 16);
          }
          __syncwarp();
        }
      }
    }
    cluster_sync();
  } else {
    asm volatile("setmaxnreg.inc.sync.aligned.u32 232;");
    LOAD_EPOCH();
    const int wg = warp >> 2;
    const int r0 = warp * 16;
    const uint32_t pK = sbase + OFF_S, pV = sbase + OFF_S + SLOT;
#define PMASKS(on, bit) const uint32_t pm0 = ((on) && t == (g >> 1)), pbit = (bit)
#define PBIT0(w) (((w) & ~pm0) | (pbit & pm0))
#define PBIT1(w) (w)
#define LANE_CONSTS() \
    int lane; asm volatile("mov.u32 %0, %%laneid;" : "=r"(lane)); \
    const int g = lane >> 2, t = lane & 3; \
    const uint32_t srowoff = (r0 + (lane & 15)) * 128, lsw = (lane & 7) << 4, lhi = (lane >> 4) << 4, lsw2 = (lane & 6) << 3; \
    (void)g; (void)t; (void)srowoff; (void)lsw; (void)lhi; (void)lsw2;
    uint32_t stgp = 0, peer;
    asm volatile("mapa.shared::cluster.u32 %0, %1, %2;" : "=r"(peer) : "r"(sbase), "r"(rank ^ 1));
    peer -= sbase;
    const uint32_t dA0 = (((sbase & 0x3FFFF) + wg * 8192) >> 4) | 0x10000u, dB0 = ((sbase & 0x3FFFF) >> 4) | 0x2000000u;
    cluster_wait();
#define DESC(lo, hi) ((uint64_t)(uint32_t)(lo) | ((uint64_t)(hi) << 32))
#define STG_ARRIVE() { __syncwarp(); if (elect_one()) mbar_arrive_local(bar_stg); }
#define STG_WAIT() { mbar_wait(bar_stg, stgp); stgp ^= 1; }
#define PROFS() do {} while (0)
#define REL(addr) { if (elect_one()) { mbar_arrive_local(addr); asm volatile("mbarrier.arrive.shared::cluster.b64 _, [%0];" :: "r"((addr) + peer) : "memory"); } }
#define QSTEP(ACC, DA, SC, PRE) { \
      const uint32_t da = (DA), db = dB0 + (ub & 0x18) * (QST >> 7); \
      mbar_wait(ub, par); \
      PRE; \
      wgmma_fence(); \
      wgmma4_n192<SC>(ACC, da, db); \
      wgmma_commit(); PROFS(); }
#define QREL() { wgmma_wait<1>(); REL(ub + 376); ub += 8; }
#define RA_CUR (dA0 + (OFF_RA >> 4) + (ub & 0x18) * (SLOT >> 7))
#define PUMP1() { QSTEP(S1, RA_CUR, 1, {}); QREL(); }
#define PUMP0() { PUMP1(); SCHED_FENCE(); }
#define PUMP() if (h == 0) PUMP1()
#define WSTEP() { \
      const uint32_t s4 = (ub - bar_full - 256) >> 1; \
      const uint32_t da = dA0 + (((uint32_t)(WO_ASLOT(par) >> s4) & 15) << 10), db = dB0 + (((uint32_t)(WO_BSLOT >> s4) & 15) << 10); \
      mbar_wait(ub, par); \
      wgmma_fence(); \
      wgmma4_n128<1>(S1, da, db); \
      wgmma_commit(); PROFS(); \
      wgmma_wait<1>(); \
      if (s4) REL(ub + 376); \
      ub += 8; }
#define PUMPS(n) { _Pragma("unroll 1") for (int i_ = 0; i_ < (n); i_++) PUMP1(); }
#define SITE(n) { if ((BMASK >> (n)) & 1) PUMP1(); SCHED_FENCE(); }
#define LNSTEP(ACC, hh) { wgmma_fence(); wgmma_n192<1, 0>(ACC, make_desc(sbase + OFF_LNA + wg * 1024, 0, 128) ^ (1ull << 62), make_desc(sbase + OFF_LNB + (hh) * 4096, 0, 128) ^ (1ull << 62)); }
#define WARP_STORE(tm, tile, col, row) { fence_proxy_async_smem(); __syncwarp(); \
      if (elect_one()) { tma_store_2d(tm, (tile) + r0 * 128, col, (row) + r0); asm volatile("cp.async.bulk.commit_group;" ::: "memory"); } __syncwarp(); }
#define PUBLISH_O() WARP_STORE(&tm_os, pO, jj * 128 + h * 64, mm * 128)
#define TILE_CONSTS(base, on, bit) \
      uint32_t ta[5]; \
      { PMASKS(on, bit); (void)pbit; ta[4] = pm0; } \
      _Pragma("unroll") for (int j = 0; j < 4; j++) ta[j] = (base) + srowoff + ((((uint32_t)j << 5) + lhi) ^ lsw); \
      PINU(ta, 5); SCHED_FENCE(); \
      const uint32_t pm0 = ta[4], pbit = (bit)
#define X_OUT(pc, W) { \
      _Pragma("unroll") for (int j = 0; j < 4; j++) \
        stsm_x4(ta[j] + (pc) * SLOT, \
                PBIT0(pack_bf16((W)[j * 8 + 0], (W)[j * 8 + 1])), PBIT0(pack_bf16((W)[j * 8 + 2], (W)[j * 8 + 3])), \
                PBIT1(pack_bf16((W)[j * 8 + 4], (W)[j * 8 + 5])), PBIT1(pack_bf16((W)[j * 8 + 6], (W)[j * 8 + 7]))); }
#define REST_P1(SKEW) { \
      mbar_wait(bar_stat2, par); \
      LNSTEP(S1, 1); \
      _Pragma("unroll 1") while (ub < bar_full + 256) { \
        if (ub == bar_full + 256 - 8 * (SKEW) && wg == 0) bar_sync<BAR_SKEW, 256>(); \
        QSTEP(S1, RA_CUR, 1, {}); \
        if (ub == bar_full + 248 && wg == 1) bar_arrive<BAR_SKEW, 256>(); \
        QREL(); \
      } \
      mbar_wait(bar_done + (31 - (SKEW)) * 8, par);        \
      wgmma_wait<0>(); \
      ACC_FENCE(S1, 96); \
      REL(bar_done + 31 * 8); \
      PROF(13); }
#define FOLD(tile, rd) { \
          LANE_CONSTS(); \
          float d[32]; \
          ACC_DEF(d, 32); \
          mbar_wait(bar_phi, 0); \
          wgmma_fence(); \
          _Pragma("unroll") for (int i = 0; i < 2; i++) { \
            const uint64_t da = make_desc((tile) + wg * 8192 + i * 64, 16, 1024); \
            const uint64_t db = make_desc(sbase + OFF_PHI + wg * 4096 + i * 2048, 16, 512) ^ (3ull << 62); \
            wgmma_n32<0>(d + i * 16, da, db); wgmma_n32<1>(d + i * 16, da + 2, db + 64); \
          } \
          wgmma_commit(); \
          PUMP0(); \
          ACC_FENCE(d, 32); \
          bar_wg(wg); \
          _Pragma("unroll") for (int i = 0; i < 4; i++) { \
            const float* x = d + (i & 1) * 8 + (i >> 1) * 2; \
            if (rd) sts128((tile) + wg * 8192 + ((warp & 3) * 16 + (i >> 1) * 8 + g) * 128 + (((2 * t + (i & 1)) ^ g) << 4), \
                           pack_bf16(x[0], x[1]), pack_bf16(x[4], x[5]), pack_bf16(x[16], x[17]), pack_bf16(x[20], x[21])); \
            else stsm_x4((tile) + srowoff + ((((uint32_t)i << 5) + lhi) ^ lsw), pack_bf16(d[i * 8], d[i * 8 + 1]), pack_bf16(d[i * 8 + 2], d[i * 8 + 3]), \
                         pack_bf16(d[i * 8 + 4], d[i * 8 + 5]), pack_bf16(d[i * 8 + 6], d[i * 8 + 7])); \
          } \
          }
#define LOAD_X0(base) \
      _Pragma("unroll") for (int j = 0; j < 8; j++) { \
        uint32_t x0, x1, x2, x3; \
        ldsm_x4((base) + (j >> 2) * SLOT + srowoff + ((((uint32_t)(j & 3) << 5) + lhi) ^ lsw), x0, x1, x2, x3); \
        S1[j * 8 + 0] = bf_lo(x0); S1[j * 8 + 1] = bf_hi(x0); S1[j * 8 + 2] = bf_lo(x1); S1[j * 8 + 3] = bf_hi(x1); \
        S1[j * 8 + 4] = bf_lo(x2); S1[j * 8 + 5] = bf_hi(x2); S1[j * 8 + 6] = bf_lo(x3); S1[j * 8 + 7] = bf_hi(x3); \
      }
#define XM_ISSUE(keep) { mbar_wait(bar_xr, par); wgmma_fence(); \
      wgmma_copy(T_, dA0 + (OFF_RA >> 4), ((keep) ? make_desc(sbase + OFF_ID + 128, 0, 0) : make_desc(sbase + OFF_ID, 128, 128)) ^ (1ull << 62), keep); }
#define COPYN(d, s, n) _Pragma("unroll") for (int i_ = 0; i_ < (n); i_++) { uint32_t c_; asm volatile("mov.b32 %0, %1;" : "=r"(c_) : "f"((s)[i_])); (d)[i_] = __uint_as_float(c_); }
#define COPY64(d, s) COPYN(d, s, 64)
#define XM_DONE(c) { ACC_FENCE(T_, 64); COPY64(S1, T_); ACC_FENCE(S1, 64); \
      __syncwarp(); if ((c) && elect_one()) mbar_arrive_local(bar_lx); }
#define LOAD_X() { float T_[64]; ACC_DEF(T_, 64); wgmma_wait<0>(); XM_ISSUE(0); wgmma_commit(); wgmma_wait<0>(); XM_DONE(true); }

    float S0[96], S1[96];
#define FIRST_STEP(l_) { const int ln_ = (l_), l = ln_; const uint32_t par = l & 1, ub = bar_full; ACC_DEF(S0, 96); QSTEP(S0, dA0 + (OFF_S >> 4), 0, {}); }
    FIRST_STEP(0);
#pragma unroll 1
    for (int l = 0;; l++) {
      const uint32_t par = l & 1;
      uint32_t ub = bar_full + 8;
      PROF(1);
      {
        LANE_CONSTS();
        uint32_t ta[4];
#pragma unroll
        for (int j = 0; j < 4; j++) ta[j] = pK + srowoff + ((((uint32_t)j << 5) + lhi) ^ lsw);
        float p0, p1, a0 = 0.f, a1 = 0.f, q0 = 0.f, q1 = 0.f;
#define STATS(j0, j1) _Pragma("unroll") for (int j = (j0); j < (j1); j++) { \
          uint32_t x[4]; \
          ldsm_x4(ta[j & 3] + (j >> 2) * SLOT, x[0], x[1], x[2], x[3]); \
          if (j == 0) { p0 = __shfl_sync(0xffffffffu, bf_lo(x[0]), lane & 28); p1 = __shfl_sync(0xffffffffu, bf_lo(x[1]), lane & 28); } \
          _Pragma("unroll") for (int i = 0; i < 4; i += 2) { \
            const float d0 = bf_lo(x[i]) - p0, d1 = bf_hi(x[i]) - p0, d2 = bf_lo(x[i + 1]) - p1, d3 = bf_hi(x[i + 1]) - p1; \
            a0 += d0 + d1; a1 += d2 + d3; \
            q0 = fmaf(d1, d1, fmaf(d0, d0, q0)); q1 = fmaf(d3, d3, fmaf(d2, d2, q1)); } } \
          asm volatile("" : "+f"(a0), "+f"(a1), "+f"(q0), "+f"(q1), "+f"(p0), "+f"(p1)); SCHED_FENCE()
        if (SB0) { STATS(0, SB0); }
        bar_wg(wg);
        QSTEP(S0, dA0 + ((OFF_S + SLOT) >> 4), 1, {});
        QREL();
        SCHED_FENCE();
        STATS(SB0, SB1);
        ACC_DEF(S1, 96);
        QSTEP(S1, dA0 + (OFF_S >> 4), 0, {});
        QREL();
        SCHED_FENCE();
        STATS(SB1, SB2);
        QSTEP(S1, dA0 + ((OFF_S + SLOT) >> 4), 1, {});
        QREL();
        SCHED_FENCE();
        STATS(SB2, SB3);
        if (SB3 < 8) {
          if (l) { asm volatile("cp.async.bulk.wait_group 0;" ::: "memory"); bar_arrive<BAR_X1, 288>(); }
          QSTEP(S0, RA_CUR, 1, {});
          SCHED_FENCE();
          STATS(SB3, 8);
          QREL();
        }
#pragma unroll
        for (int o = 1; o <= 2; o <<= 1) {
          a0 += __shfl_xor_sync(0xffffffffu, a0, o); a1 += __shfl_xor_sync(0xffffffffu, a1, o);
          q0 += __shfl_xor_sync(0xffffffffu, q0, o); q1 += __shfl_xor_sync(0xffffffffu, q1, o);
        }
        if (t == 1) { a0 = a1; q0 = q1; p0 = p1; }
        if (t < 2) st_b64(g_stats + (size_t)(mm * 128 + r0 + g + t * 8) * 8 + jj, __float_as_uint(fmaf(a0, 1.f / 128.f, p0)),
                          (__float_as_uint(fmaxf(fmaf(a0 * (-1.f / 128.f), a0, q0), 0.f)) & ~3u) | STAT_TAG(l));
        if (SB3 == 8 && l) { asm volatile("cp.async.bulk.wait_group 0;" ::: "memory"); bar_arrive<BAR_X1, 288>(); }
#pragma unroll 1
        for (int i = (SB3 < 8); i < 14; i++) {
          QSTEP(S0, RA_CUR, 1, {});
          if (i == 0) PROF(2);
          QREL();
        }
      }
      LANE_CONSTS();
      mbar_wait(bar_stat, par);
      LNSTEP(S0, 0);
      wgmma_commit();
      const float rs0 = lds32f(sbase + OFF_ST + (r0 + g) * 4), rs1 = lds32f(sbase + OFF_ST + (r0 + g + 8) * 4);
      PUMP0();
      ACC_FENCE(S0, 96);
      PROF(3);
      if (!par) {
        constexpr uint32_t par = 0;
        uint32_t qa[16];
        uint32_t kf[32], vf[32];
#define DRAIN_A(ACC, hp, PMP) { \
          LANE_CONSTS(); \
          FRAG(kf + 16, ACC + 32, 0, (hp) * 2); \
          PMP; \
          FRAG(vf + 16, ACC + 64, 1, (hp) * 2 + 1); \
          _Pragma("unroll") for (int i_ = 0; i_ < 16; i_++) qa[i_] = pack_bf16(ACC[2 * i_], ACC[2 * i_ + 1]); \
          PINU(qa, 16); }
        DRAIN_A(S0, 0, PUMP0());
        if (l == 0 && NLAYERS > 1) {
#pragma unroll 1
          for (int rd = 1; rd >= 0; rd--) {
            FOLD(sbase + (12 - rd) * SLOT, rd);
            fence_proxy_async_smem();
            asm volatile("bar.arrive %0, 288;" :: "r"(BAR_WF + 1 - rd) : "memory");
          }
        }
        PUMPS(FPUMP);
        if (l == 0 && NLAYERS > 1) mbar_wait(bar_phi, 1);
#pragma unroll 1
        for (int h = 0; h < 2; h++) {
          const uint32_t pO = sbase + (h ? 3 : 12) * SLOT;
          PROFH(4, 16);
          LANE_CONSTS();
          if (XA && h) {
            float T_[64];
            ACC_DEF(T_, 64);
            if (XA == 2) { FRAG_PUT(kf + 16, 10); }
            XM_ISSUE(0); wgmma_commit();
            SCHED_FENCE();
            if (XA == 1) { FRAG_PUT(kf + 16, 10); }
            FRAG_PUT(vf + 16, 11);
            STG_ARRIVE();
            SCHED_FENCE();
            wgmma_wait<0>(); XM_DONE(true);
          } else {
            FRAG_PUT(kf + 16, 10); FRAG_PUT(vf + 16, 11);
            STG_ARRIVE();
          }
          if (h) { if (!XA) LOAD_X(); if (AW0) WSTEP(); } else PUMPS(HPUMP2);
          const bool e = g & 1, hb = (2 * t + (g & 1)) <= g;
          uint32_t sel[3] = {e ? 0x1044u : 0x4410u, hb ? 0x4444u : (e ? 0x3244u : 0x4432u), hb ? (e ? 0x3244u : 0x4432u) : 0x4444u};
          PINU(sel, 3);
          TILE_CONSTS(pO, true, O_BIT(l));
          const uint32_t selA = sel[0], selL = sel[1], selH = sel[2];
          STG_WAIT();
          if (warp == 0) mbar_wait(bar_halo, h);
          FRAG_GET(kf, 10);
          PROFH(5, 17);
          float s[2][4][4];
#pragma unroll
          for (int ks = 0; ks < 2; ks++)
#pragma unroll
            for (int i = 0; i < 8; i++) {
              const int hh = (i >> 1) & 1, jb = (i & 1) + (~i >> 1 & 2);
              const uint32_t* b = kf + (jb >> 1) * 16 + hh * 8 + ks * 4 + (jb & 1) * 2;
              if (ks) mma_bf16(s[hh][jb], qa[hh * 8 + 4], qa[hh * 8 + 5], qa[hh * 8 + 6], qa[hh * 8 + 7], b[0], b[1]);
              else mma_bf16_z(s[hh][jb], qa[hh * 8], qa[hh * 8 + 1], qa[hh * 8 + 2], qa[hh * 8 + 3], b[0], b[1]);
            }
          PUMP();
          PROFH(6, 18);
          float va[2][2], vb[2][2], mx[2][2];
#pragma unroll
          for (int hh = 0; hh < 2; hh++) {
            va[hh][0] = e ? s[hh][1][1] : s[hh][1][0];
            vb[hh][0] = hb ? (e ? s[hh][2][1] : s[hh][2][0]) : (e ? s[hh][0][1] : s[hh][0][0]);
            va[hh][1] = e ? s[hh][2][3] : s[hh][2][2];
            vb[hh][1] = hb ? (e ? s[hh][3][3] : s[hh][3][2]) : (e ? s[hh][1][3] : s[hh][1][2]);
          }
          if (warp == 0 && mm == 0) {
#pragma unroll
            for (int hh = 0; hh < 2; hh++) { va[hh][0] = -INFINITY; if (!hb) { vb[hh][0] = -INFINITY; vb[hh][1] = -INFINITY; } }
          }
#pragma unroll
          for (int i = 0; i < 4; i++) mx[i >> 1][i & 1] = fmaxf(va[i >> 1][i & 1], vb[i >> 1][i & 1]);
#pragma unroll
          for (int o = 1; o <= 2; o <<= 1)
#pragma unroll
            for (int i = 0; i < 4; i++) mx[i >> 1][i & 1] = fmaxf(mx[i >> 1][i & 1], __shfl_xor_sync(0xffffffffu, mx[i >> 1][i & 1], o));
          const float sc0 = rs0 * (0.17677669529663687f * LOG2E), sc1 = rs1 * (0.17677669529663687f * LOG2E);
#pragma unroll
          for (int i = 0; i < 4; i++) {
            const float sc = (i & 1) ? sc1 : sc0, m = mx[i >> 1][i & 1];
            va[i >> 1][i & 1] = ex2((va[i >> 1][i & 1] - m) * sc); vb[i >> 1][i & 1] = ex2((vb[i >> 1][i & 1] - m) * sc);
            mx[i >> 1][i & 1] = va[i >> 1][i & 1] + vb[i >> 1][i & 1];
          }
          if (h == 0 && ASITE) { PIN(&va[0][0], 4); PIN(&vb[0][0], 4); PIN(&mx[0][0], 4); PUMP1(); }
          if (warp == 0) mbar_wait(bar_halo + 8, h);
          FRAG_GET(vf, 11);
#pragma unroll
          for (int o = 1; o <= 2; o <<= 1)
#pragma unroll
            for (int i = 0; i < 4; i++) mx[i >> 1][i & 1] += __shfl_xor_sync(0xffffffffu, mx[i >> 1][i & 1], o);
          float o[2][4][4];
          uint32_t pa[2][8];
#pragma unroll
          for (int hh = 0; hh < 2; hh++) {
            const float i0 = rcp_fast(mx[hh][0]), i1 = rcp_fast(mx[hh][1]);
            const uint32_t w0 = pack_bf16(va[hh][0] * i0, vb[hh][0] * i0), w1 = pack_bf16(va[hh][1] * i1, vb[hh][1] * i1);
            pa[hh][0] = __byte_perm(w0, 0, selL); pa[hh][2] = __byte_perm(w0, 0, selA); pa[hh][3] = __byte_perm(w1, 0, selL);
            pa[hh][4] = __byte_perm(w0, 0, selH); pa[hh][5] = __byte_perm(w1, 0, selA); pa[hh][7] = __byte_perm(w1, 0, selH);
            pa[hh][1] = pa[hh][0] & pa[hh][4]; pa[hh][6] = pa[hh][3] & pa[hh][7];
          }
          PROFH(7, 19);
#pragma unroll
          for (int i = 0; i < 8; i++) mma_bf16_z(o[i >> 2][i & 3], pa[i >> 2][4], pa[i >> 2][5], pa[i >> 2][6], pa[i >> 2][7], vf[16 + 2 * i], vf[17 + 2 * i]);
#pragma unroll
          for (int i = 0; i < 8; i++) mma_bf16(o[i >> 2][i & 3], pa[i >> 2][0], pa[i >> 2][1], pa[i >> 2][2], pa[i >> 2][3], vf[2 * i], vf[2 * i + 1]);
          if (h == 0) PUMP1() else mbar_wait(bar_done + 30 * 8, par);
          if (NLAYERS > 1) mbar_wait(bar_phi + 8, 0);
#pragma unroll
          for (int i = 0; i < 4; i++) {
            const int hh = i >> 1, dp = i & 1;
            stsm_x4(ta[i],
                    PBIT0(pack_bf16(o[hh][dp * 2][0], o[hh][dp * 2][1])), PBIT0(pack_bf16(o[hh][dp * 2][2], o[hh][dp * 2][3])),
                    PBIT1(pack_bf16(o[hh][dp * 2 + 1][0], o[hh][dp * 2 + 1][1])), PBIT1(pack_bf16(o[hh][dp * 2 + 1][2], o[hh][dp * 2 + 1][3])));
          }
          PUBLISH_O();
          PROFH(11, 23);
          if (h) break;
          REST_P1(ASKEW);
          asm volatile("cp.async.bulk.wait_group.read 0;" ::: "memory");
          DRAIN_A(S1, 1, {});
        }
      } else {
        constexpr uint32_t par = 1;
        float st[32];
        const float c0 = rs0 * LOG2E, c1 = rs1 * LOG2E;
        { V_ADDR(pV); STAGE_V(S0 + 64); }
        if (warp < 2) sts128(sbase + OFF_ONES + warp * 512 + lane * 16, 0x3F803F80u, 0x3F803F80u, 0x3F803F80u, 0x3F803F80u);
        scale32(st, S0, c0, c1);
        PIN(st, 32);
#define KV_MMA(vs) { \
          const uint32_t dp = dA0 + 12 * 1024 - wg * 2560, dv = dA0 + (vs) * 1024 + ((OFF_ONES - (vs) * SLOT - 16) << 12) - wg * (512 << 16); \
          STG_WAIT(); \
          wgmma_fence(); \
          _Pragma("unroll") for (int ks = 0; ks < 8; ks++) { \
            const uint64_t a = DESC(dp + ks * 128, 0x40000040), b = DESC(dv + ks * (64 - (64 << 16)), 0x80000020); \
            if (ks == 0) wgmma_n40<0, 1>(kv, a, b); else wgmma_n40<1, 1>(kv, a, b); } \
          wgmma_commit(); }
#define KV_RED(hp) { \
          float* kvg = g_kv[l >> 1] + (jj * 4 + (hp) * 2) * KVH + warp * 768 + lane * 4; \
          _Pragma("unroll") for (int i = 0; i < 5; i++) red_v4(kvg + i * 128, kv[i * 3], kv[i * 3 + 1], kv[i * 3 + 2], 1.f); \
          red_v4(kvg + 640, kv[15], kv[16], kv[18], 1.f); }
#define KV_RED1(i) if (h) red_v4(g_kv[l >> 1] + (jj * 4) * KVH + warp * 768 + lane * 4 + (i) * 128, S0[32 + (i) * 3], S0[33 + (i) * 3], S0[34 + (i) * 3], 1.f)
#define KV_REDS(n) { _Pragma("unroll") for (int i_ = 0; i_ < 6; i_++) if (RPACE && ((RPACE >> (4 * i_)) & 15) == (n)) KV_RED1(i_); }
#define KV_LOAD(hp) { \
          const uint4* kvg = reinterpret_cast<const uint4*>(g_kv[l >> 1] + (jj * 4 + (hp) * 2) * KVH) + warp * 192 + lane; \
          _Pragma("unroll") for (int i = 0; i < 6; i++) v[i] = ld_b128(kvg + i * 32); }
#define KVV(i) __uint_as_float((i) % 3 == 0 ? v[(i) / 3].x : ((i) % 3 == 1 ? v[(i) / 3].y : v[(i) / 3].z))
#define KV_TILE(hp) { \
          _Pragma("unroll 1") for (int it = 0; it < (1 << 16); it++) { \
            if (__all_sync(0xffffffffu, (v[0].w & v[1].w & v[2].w & v[3].w & v[4].w & v[5].w) == 0x41800000u)) break; \
            RETRY_COUNT(); \
            KV_LOAD(hp); \
          } \
          if (hp) PROF(26); else PROF(25); \
          const uint32_t e = lane & 7, jt = ((lane >> 1) & 4) + (e >> 1); \
          const uint32_t row = ((((warp >> 1) ^ wg) & 1) << 5) + ((jt & 1) << 4) + ((warp & 1) << 3) + (jt & 6) + (e & 1); \
          const uint32_t kd = pV + wg * 8192 + row * 128, ksw = (row & 7) << 4; \
          _Pragma("unroll") for (int i = 0; i < 2; i++) \
            stsm_x4(kd + ((i * 32 + lhi) ^ ksw), pack_bf16(KVV(i * 8), KVV(i * 8 + 1)), pack_bf16(KVV(i * 8 + 2), KVV(i * 8 + 3)), \
                    pack_bf16(KVV(i * 8 + 4), KVV(i * 8 + 5)), pack_bf16(KVV(i * 8 + 6), KVV(i * 8 + 7))); \
          stsm_x4(kd + ((64u + lhi) ^ ksw), pack_bf16(KVV(16), 1.f), pack_bf16(KVV(17), 1.f), 0u, 0u); }
#pragma unroll 1
        for (int h = 0; h < 2; h++) {
          PROFH(4, 6);
          SITE(0);
          LANE_CONSTS();
          const uint32_t dsw = (uint32_t)(g ^ (2 * t)) << 4, dst = ((t & 2) ? pK : sbase + 12 * SLOT) + (r0 + g) * 128;
          float e[16], f[16];
          KV_REDS(1);
          float sa = exps16_<0>(e, st);
          exps16_fix<0>(e, st, sa);
          asm volatile("" : "+f"(sa)); PIN(e, 16); SITE(1);
          if (h) STG_WAIT();
          KV_REDS(2);
          store16(e, sa, dst, dsw, 4);
          float sb = exps16_<1>(f, st);
          exps16_fix<1>(f, st, sb);
          asm volatile("" : "+f"(sb)); PIN(f, 16); SITE(2);
          KV_REDS(3);
          store16(f, sb, dst, dsw, 0);
          float sc = exps16_<0>(e, st + 2);
          exps16_fix<0>(e, st + 2, sc);
          asm volatile("" : "+f"(sc)); PIN(e, 16); SITE(3);
          KV_REDS(4);
          store16(e, sc, dst + 1024, dsw, 4);
          float sd = exps16_<1>(f, st + 2);
          exps16_fix<1>(f, st + 2, sd);
          asm volatile("" : "+f"(sd)); PIN(f, 16); SITE(4);
          store16(f, sd, dst + 1024, dsw, 0);
          PROFH(5, 7);
          if (h) break;
          {
            float kv[20];
            ACC_DEF(kv, 20);
            fence_proxy_async_smem();
            STG_ARRIVE();
            KV_MMA(11);
            PUMP0();
            ACC_FENCE(kv, 20);
            if (!RPACE) KV_RED(0);
            STG_ARRIVE();
            scale32(st, S0 + 32, c0, c1);
            PIN(st, 32);
            if (RPACE) {
              kv[17] = kv[18];
              COPYN(S0 + 32, kv, 18);
              const int h = 1;
              KV_REDS(0);
            }
          }
        }
        bool big;
        uint4 v[6];
        {
          float kv[20];
          if (KT0) { LANE_CONSTS(); KV_LOAD(0); }
          mbar_wait(bar_stat2, par);
          LNSTEP(S1, 1);
          ub = bar_full + 240;
          PUMP1();
          if (wg == 0) bar_sync<BAR_SKEW, 256>();
          QSTEP(S1, RA_CUR, 1, {});
          if (wg == 1) bar_arrive<BAR_SKEW, 256>();
          QREL();
          if (KT0 == 2) { LANE_CONSTS(); KV_TILE(0); }
          LANE_CONSTS();
          V_ADDR(sbase + 3 * SLOT);
          PINU(va_, 2);
          mbar_wait(bar_done + 30 * 8, par);
          wgmma_wait<0>();
          ACC_FENCE(S1, 96);
          if (!(RLATE & 2)) REL(bar_done + 31 * 8);
          PROF(13);
          STAGE_V(S1 + 64);
          fence_proxy_async_smem();
          STG_ARRIVE();
          if (RLATE & 2) REL(bar_done + 31 * 8);
          scale32(st, S1, c0, c1);
          PIN(st, 32);
          PROF(16);
          ACC_DEF(kv, 20);
          KV_MMA(3);
          SCHED_FENCE();
          if (!KT0) KV_LOAD(0);
          big = any_big(st);
          if (EROT > 0) { phiq_a(st, big); PIN(st, 16); }
          SCHED_FENCE();
          wgmma_wait<0>();
          ACC_FENCE(kv, 20);
          KV_RED(1);
          PROF(17);
        }
#pragma unroll 1
        for (int h = 0; h < 2; h++) {
          const uint32_t pO = sbase + (h ? 3 : 8) * SLOT;
          LANE_CONSTS();
          uint32_t fq[32];
          if (EROT < 1) phiq_a(st, big);
          if (EMRG == 0) { phiq_b<0>(fq, st, big); PINU(fq, 16); }
          if (EMRG == 2) { phiq_b<1>(fq, st, big); PINU(fq, 16); PIN(st + 16, 16); }
          PROFH(18, 32);
          SCHED_FENCE();
          if (h) {
            asm volatile("cp.async.bulk.wait_group.read 0;" ::: "memory");
            mbar_wait(bar_lx, par);
          }
          if (h || KT0 < 2) {
            KV_TILE(h);
            fence_proxy_async_smem();
            STG_ARRIVE();
          }
          SCHED_FENCE();
          if (EMRG == 0) { phiq_a(st + 16, big); PIN(st + 16, 16); }
          if (EMRG == 1) { phiq_b<1>(fq, st, big); PINU(fq, 16); PIN(st + 16, 16); }
          if (h || KT0 < 2) STG_WAIT();
          wgmma_wait<0>();
          ACC_FENCE(S1, 64);
          float T_[64];
          if (XB == 3) { COPY64(T_, S1); }
          PROFH(19, 33);
          float o[4][20];
#define O_MMA(hh) { \
            const uint64_t db = make_desc(pV + (hh) * 8192, 16, 1024); \
            ACC_DEF(o[(hh) * 2], 20); ACC_DEF(o[(hh) * 2 + 1], 20); \
            wgmma_fence(); \
            wgmma_n40_rs<0>(o[(hh) * 2], fq + (hh) * 16, db + 256); wgmma_n40_rs<0>(o[(hh) * 2 + 1], fq + (hh) * 16 + 8, db); \
            wgmma_n40_rs<1>(o[(hh) * 2], fq + (hh) * 16 + 4, db + 384); wgmma_n40_rs<1>(o[(hh) * 2 + 1], fq + (hh) * 16 + 12, db + 128); \
            wgmma_commit(); }
          O_MMA(0);
          SCHED_FENCE();
          phiq_b<0>(fq + 16, st + 16, big); PINU(fq + 16, 16);
          SCHED_FENCE();
          PMASKS(true, O_BIT(l));
#pragma unroll
          for (int hh = 0; hh < 2; hh++) {
            if (hh && !OW) O_MMA(1);
            if (XB == 3 && hh) { scale32(st, T_ + 32, c0, c1); PIN(st, 32); XM_ISSUE(h); wgmma_commit(); wgmma_wait<1>(); } else
            wgmma_wait<0>();
            ACC_FENCE(o[hh * 2], 20); ACC_FENCE(o[hh * 2 + 1], 20);
            if (!hh && OW) { O_MMA(1); SCHED_FENCE(); }
            const float* x = o[hh * 2];
            const float* y = o[hh * 2 + 1];
            const float sx0 = x[17] * 0x1p-40f, sy0 = y[17] * 0x1p-40f, sx1 = x[19] * 0x1p-40f, sy1 = y[19] * 0x1p-40f;
            const float i0 = rcp_fast(fmaf(fmaf(x[17], 1e-6f, x[16]), sy0, y[16] * sx0)), i1 = rcp_fast(fmaf(fmaf(x[19], 1e-6f, x[18]), sy1, y[18] * sx1));
            const float ax0 = sy0 * i0, ay0 = sx0 * i0, ax1 = sy1 * i1, ay1 = sx1 * i1;
#pragma unroll
            for (int dp = 0; dp < 2; dp++)
              stsm_x4(pO + srowoff + ((hh * 64 + dp * 32 + lhi) ^ lsw),
                      PBIT0(pack_bf16(fmaf(x[dp * 8], ax0, y[dp * 8] * ay0), fmaf(x[dp * 8 + 1], ax0, y[dp * 8 + 1] * ay0))),
                      PBIT0(pack_bf16(fmaf(x[dp * 8 + 2], ax1, y[dp * 8 + 2] * ay1), fmaf(x[dp * 8 + 3], ax1, y[dp * 8 + 3] * ay1))),
                      PBIT1(pack_bf16(fmaf(x[dp * 8 + 4], ax0, y[dp * 8 + 4] * ay0), fmaf(x[dp * 8 + 5], ax0, y[dp * 8 + 5] * ay0))),
                      PBIT1(pack_bf16(fmaf(x[dp * 8 + 6], ax1, y[dp * 8 + 6] * ay1), fmaf(x[dp * 8 + 7], ax1, y[dp * 8 + 7] * ay1))));
          }
          PUBLISH_O();
          if (XB == 3) { wgmma_wait<0>(); XM_DONE(h == 0); }
          PROFH(20, 34);
          if (h) break;
          if (KVL == 2) { KV_LOAD(1); SCHED_FENCE(); }
          if (!XB) {
            scale32(st, S1 + 32, c0, c1);
            PIN(st, 32);
            LOAD_X();
          }
          if (XB == 4) {
            scale32(st, S1 + 32, c0, c1);
            PIN(st, 32);
            ACC_DEF(T_, 64);
            XM_ISSUE(0); wgmma_commit();
            SCHED_FENCE();
            KV_LOAD(1);
            big = any_big(st);
            SCHED_FENCE();
            wgmma_wait<0>(); XM_DONE(true);
          }
          bar_wg(wg);
          WSTEP();
          SCHED_FENCE();
          if (KVL == 0 && XB != 4) KV_LOAD(1);
          if (XB != 4) big = any_big(st);
          if (KVL == 1) { SCHED_FENCE(); KV_LOAD(1); }
          if (EROT > 0) { phiq_a(st, big); PIN(st, 16); }
          PROF(31);
        }
      }
      __syncwarp();
      if (elect_one()) mbar_arrive_local(bar_epi);
      bar_wg(wg);
#pragma unroll 1
      while (ub < bar_full + 384) {
        WSTEP();
        if (ub == bar_full + 8 * 41) { asm volatile("cp.async.bulk.wait_group.read 0;" ::: "memory"); PROF(35); }
        if (ub == bar_full + 8 * 42) PROF(36);
      }
      {
        float Wb[32];
        LANE_CONSTS();
        TILE_CONSTS(pK, l < NLAYERS - 1, X_BIT(l));
        wgmma_wait<0>();
        ACC_FENCE(S1, 64);
        COPYN(Wb, S1 + 32, 32);
        PROF(37);
        X_OUT(0, S1);
        WARP_STORE(l < NLAYERS - 1 ? &tm_os : &tm_xo, pK, jj * 128, mm * 128 + (l < NLAYERS - 1 ? S_LEN : 0));
        if (l == NLAYERS - 1) { PMASKS(false, 0); X_OUT(1, Wb); break; }
        REL(bar_done + 47 * 8);
        PROF(38);
        bar_wg(wg);
        FIRST_STEP(l + 1);
        PROF(39);
        { PMASKS(false, 0); X_OUT(1, Wb); }
        fence_proxy_async_smem();
      }
    }
    WARP_STORE(&tm_xo, pV, jj * 128 + 64, mm * 128);
    asm volatile("cp.async.bulk.wait_group.read 0;" ::: "memory");
    cluster_sync();
  }
}

typedef CUresult (*PFN_encode)(CUtensorMap*, CUtensorMapDataType, cuuint32_t, void*, const cuuint64_t*, const cuuint64_t*,
                               const cuuint32_t*, const cuuint32_t*, CUtensorMapInterleave, CUtensorMapSwizzle,
                               CUtensorMapL2promotion, CUtensorMapFloatOOBfill);

CUtensorMap make_map(PFN_encode enc, const void* ptr, uint64_t inner, uint64_t outer, uint32_t box_inner, uint32_t box_outer,
                     CUtensorMapSwizzle swz = CU_TENSOR_MAP_SWIZZLE_128B, int promo = CU_TENSOR_MAP_L2_PROMOTION_L2_256B) {
  CUtensorMap m;
  cuuint64_t dims[2] = {inner, outer};
  cuuint64_t strides[1] = {inner * 2};
  cuuint32_t box[2] = {box_inner, box_outer};
  cuuint32_t es[2] = {1, 1};
  enc(&m, CU_TENSOR_MAP_DATA_TYPE_BFLOAT16, 2, const_cast<void*>(ptr), dims, strides, box, es, CU_TENSOR_MAP_INTERLEAVE_NONE,
      swz, (CUtensorMapL2promotion)promo, CU_TENSOR_MAP_FLOAT_OOB_FILL_NONE);
  return m;
}

}

extern "C" void kernel_launch(void* const* d_in, const int* in_sizes, int n_in, void* d_out, int out_size) {
  (void)in_sizes; (void)n_in; (void)out_size;
  static PFN_encode enc = nullptr;
  if (!enc) {
    void* fn = nullptr;
    cudaDriverEntryPointQueryResult qr;
    cudaGetDriverEntryPoint("cuTensorMapEncodeTiled", &fn, cudaEnableDefault, &qr);
    enc = (PFN_encode)fn;
    cudaFuncSetAttribute(mega_kernel, cudaFuncAttributeMaxDynamicSharedMemorySize, SMEM_BYTES);
  }
  Params prm;
  prm.x0 = (const __nv_bfloat16*)d_in[0];
  prm.wA_qkv = (const __nv_bfloat16*)d_in[1];
  prm.wA_o = (const __nv_bfloat16*)d_in[2];
  prm.wB_qkv = (const __nv_bfloat16*)d_in[4];
  prm.wB_phi = (const __nv_bfloat16*)d_in[5];
  prm.wB_o = (const __nv_bfloat16*)d_in[6];
  prm.out = (__nv_bfloat16*)d_out;
  void *obuf = nullptr, *wf = nullptr;
  cudaGetSymbolAddress(&obuf, g_obuf);
  cudaGetSymbolAddress(&wf, g_wfold);
  CUtensorMap tm_x0 = make_map(enc, d_in[0], D_MODEL, S_LEN, 64, 128, CU_TENSOR_MAP_SWIZZLE_128B, XPROMO);
  CUtensorMap tm_xo = make_map(enc, d_out, D_MODEL, S_LEN, 64, 16);
  CUtensorMap tm_os = make_map(enc, obuf, D_MODEL, 2 * S_LEN, 64, 16);
  CUtensorMap tm_o = make_map(enc, obuf, D_MODEL, 2 * S_LEN, 64, 128, CU_TENSOR_MAP_SWIZZLE_128B, OPROMO);
  CUtensorMap tm_wf = make_map(enc, wf, 2048, D_MODEL, 64, 32);
  CUtensorMap tm_wqA = make_map(enc, d_in[1], 3 * D_MODEL, D_MODEL, 64, 32, CU_TENSOR_MAP_SWIZZLE_128B, WPROMO);
  CUtensorMap tm_wqB = make_map(enc, prm.wB_qkv, 3 * D_MODEL, D_MODEL, 64, 32);
  CUtensorMap tm_woA = make_map(enc, prm.wA_o, D_MODEL, D_MODEL, 64, 64);
  CUtensorMap tm_woB = make_map(enc, prm.wB_o, D_MODEL, D_MODEL, 64, 64);
  CUtensorMap tm_phi = make_map(enc, prm.wB_phi, 32, 1024, 32, 128, CU_TENSOR_MAP_SWIZZLE_64B);
  mega_kernel<<<NMAIN + NAUX, 384, SMEM_BYTES>>>(tm_x0, tm_xo, tm_os, tm_o, tm_wf, tm_wqA, tm_wqB, tm_woA, tm_woB, tm_phi, prm);
}
```

```cpp
#include <cuda_runtime.h>
#include <cuda.h>
#include <cuda_bf16.h>
#include <stdint.h>

#define NLAYERS 4

#define STAG1 0
#define HPUMP1 2
#define HPUMP2 1
#define ASKEW 2
#define FPUMP 3
#define PFGAP 100
#define POLLGAP 120
#define OW 1
#define AW0 1
#define RLATE 3
#define FSTART 0
#define MAPV 1
#define HW1 29
#define XPACE 0x06050401000000ull
#define XP0 4
#define HW0 18
#define XD 4
#define WFGAP 50
#define KT0 2
#define W23 0
#define AX 0
#define PF0 1
#define ORD 0
#define EARLY (2 + ORD)
#define UPS(u) (ORD ? (u) & 1 : (u) >> 1)
#define USL(u) (ORD ? (u) >> 1 : (u) & 1)
#define BIGLIM 3600.f
#define SUMLO 0x1p-100f
#define SUMHI 0x1p100f
#define EROT 1
#define FINW 0
#define AHOIST 1
#define EMRG 1
#define XPROMO 2
#define OPROMO 3
#define STAG2 300
#define WPROMO 3
#define SB0 2
#define SB1 4
#define SB2 6
#define KVL 0
#define BMASK 0x1F
#define ASITE 1
#define NEWOPTS
#define PAIR 2
#define PPOS 1
#define PPOS0 1
#define NOBW 0
#define CPA 0
#define PFW 0
#define FD0 0
#define FD1 3
#define RPACE 0x221100
#define XA 0
#define XB 4
#define XMMA 1
namespace {

constexpr int S_LEN = 2048, D_MODEL = 1024;
constexpr int NAUX = 4, NMAIN = 128;
constexpr int SLOT = 16384;
constexpr int QST = 24576;
constexpr int OFF_RA = 6 * SLOT, OFF_S = 10 * SLOT;
constexpr int OFF_HALO = 13 * SLOT, OFF_LNB = OFF_HALO  , OFF_ONES = OFF_HALO + 3072;
constexpr int OFF_ST = OFF_HALO + 7168  , OFF_ID = OFF_HALO + 7680, OFF_PHI = OFF_HALO + 8192;
constexpr int OFF_BAR = 14 * SLOT;
constexpr int OFF_LNA = OFF_BAR + 1024;
constexpr int SMEM_BYTES = OFF_LNA + 2048;
#define WO_ASLOT(par) ((par) ? 0x9876CAB39876CA98ull : 0x98C76BA398C7698Cull)
constexpr unsigned long long WO_BSLOT = 0x5432105421054210ull;
__device__ __forceinline__ int srcb(int j, int i) { return (i + (i >= j)) & 7; }
__device__ __forceinline__ int kslice(int j, int i) { return i < 2 ? 2 * j + i : (i < 9 ? 2 * srcb(j, i - 2) : 2 * srcb(j, i - 9) + 1); }
__device__ __forceinline__ int wslice(int j, int s) { return 2 * ((s & 7) ? srcb(j, (s & 7) - 1) : j) + (s >> 3); }
constexpr int KVH = 6 * 128 * 4;

struct __align__(128) Flag { unsigned v; unsigned pad[31]; };
struct Flags {
  Flag xready[4][16];
  Flag wfready[8];
  Flag done;
  Flag epoch;
};

__device__ Flags g_flags;
__device__ __nv_bfloat16 g_obuf[2 * S_LEN * D_MODEL];
#define O_BIT(l) ((epoch * NLAYERS + (l) + 1) & 1u)
#define X_BIT(l) ((epoch * (NLAYERS - 1) + (l) + 1) & 1u)
__device__ __nv_bfloat16 g_wfold[D_MODEL * 2048];
__device__ uint4 g_halo[16 * 8 * 512];
__device__ __align__(128) float g_kv[2][32 * KVH];
__device__ __align__(128) uint2 g_colsum[2][1536][2];
__device__ __align__(128) uint2 g_stats[S_LEN * 8];
#define H_BIT(l) (NLAYERS > 2 ? (uint32_t)((l) == 0) : (ep1 & 1))
#define STAT_TAG(l) ((ep1 * NLAYERS + (l) + 1) & 3u)

#define RETRY_COUNT()
#define PRL 0
#define PRU 0
#define PROFL 1
#define PROFW 0
#define PROFT(i) do {} while (0)
#define PROF(i) do {} while (0)
#define PROFH(i, j) do {} while (0)

__device__ __forceinline__ uint32_t smem_u32(const void* p) { return (uint32_t)__cvta_generic_to_shared(p); }
__device__ __forceinline__ bool elect_one() {
  uint32_t p;
  asm volatile("{\n.reg .pred p;\nelect.sync _|p, 0xffffffff;\nselp.u32 %0, 1, 0, p;\n}\n" : "=r"(p));
  return p != 0;
}
__device__ __forceinline__ void mbar_init(uint32_t bar, uint32_t cnt) {
  asm volatile("mbarrier.init.shared::cta.b64 [%0], %1;" :: "r"(bar), "r"(cnt));
}
__device__ __forceinline__ void mbar_expect_tx(uint32_t bar, uint32_t bytes) {
  asm volatile("mbarrier.arrive.expect_tx.shared::cta.b64 _, [%0], %1;" :: "r"(bar), "r"(bytes) : "memory");
}
#define mbar_wait(bar, parity) \
  asm volatile("{\n.reg .pred p, q;\nW_%=:\nmbarrier.try_wait.parity.shared::cta.b64 p, [%1], %2;\nadd.s32 %0, %0, -1;\n" \
               "setp.gt.and.s32 q, %0, 0, !p;\n@q bra.uni W_%=;\n}\n" : "+r"(budget) : "r"((uint32_t)(bar)), "r"((uint32_t)(parity)) : "memory")
#define mbar_wait_sl(bar, parity) \
  asm volatile("{\n.reg .pred p, q;\nW_%=:\nmbarrier.try_wait.parity.shared::cta.b64 p, [%1], %2, 20000;\nadd.s32 %0, %0, -64;\n" \
               "setp.gt.and.s32 q, %0, 0, !p;\n@q bra.uni W_%=;\n}\n" : "+r"(budget) : "r"((uint32_t)(bar)), "r"((uint32_t)(parity)) : "memory")
__device__ __forceinline__ void mbar_arrive_local(uint32_t bar) {
  asm volatile("mbarrier.arrive.shared::cta.b64 _, [%0];" :: "r"(bar) : "memory");
}
__device__ __forceinline__ void tma_load_2d(uint32_t dst, const CUtensorMap* tm, uint32_t bar, int c0, int c1) {
  asm volatile("cp.async.bulk.tensor.2d.shared::cluster.global.mbarrier::complete_tx::bytes [%0], [%1, {%3, %4}], [%2];"
               :: "r"(dst), "l"(tm), "r"(bar), "r"(c0), "r"(c1) : "memory");
}
__device__ __forceinline__ void tma_load_2d_mc(uint32_t dst, const CUtensorMap* tm, uint32_t bar, int c0, int c1) {
  asm volatile("cp.async.bulk.tensor.2d.shared::cluster.global.mbarrier::complete_tx::bytes.multicast::cluster [%0], [%1, {%3, %4}], [%2], %5;"
               :: "r"(dst), "l"(tm), "r"(bar), "r"(c0), "r"(c1), "h"((uint16_t)3) : "memory");
}
__device__ __forceinline__ void tma_store_2d(const CUtensorMap* tm, uint32_t src, int c0, int c1) {
  asm volatile("cp.async.bulk.tensor.2d.global.shared::cta.bulk_group [%0, {%2, %3}], [%1];"
               :: "l"(tm), "r"(src), "r"(c0), "r"(c1) : "memory");
}
__device__ __forceinline__ void bulk_commit_wait() {
  asm volatile("cp.async.bulk.commit_group;\ncp.async.bulk.wait_group 0;" ::: "memory");
}
__device__ __forceinline__ void prefetch_tmap(const CUtensorMap* tm) {
  asm volatile("prefetch.tensormap [%0];" :: "l"(tm) : "memory");
}
__device__ __forceinline__ void fence_proxy_async_global() { asm volatile("fence.proxy.async.global;" ::: "memory"); }
__device__ __forceinline__ void fence_proxy_async_smem() { asm volatile("fence.proxy.async.shared::cta;" ::: "memory"); }
__device__ __forceinline__ unsigned ld_relaxed(const unsigned* p) {
  unsigned v;
  asm volatile("ld.relaxed.gpu.global.u32 %0, [%1];" : "=r"(v) : "l"(p) : "memory");
  return v;
}
__device__ __forceinline__ void fence_acquire() { asm volatile("fence.acquire.gpu;" ::: "memory"); }
__device__ __forceinline__ void wait_flag(const unsigned* p, unsigned target) {
  int it = 0;
  while ((int)(ld_relaxed(p) - target) < 0 && ++it < (1 << 20)) {}
  fence_acquire();
}
__device__ __forceinline__ void signal_release(unsigned* p) {
  asm volatile("red.release.gpu.global.add.u32 [%0], 1;" :: "l"(p) : "memory");
}
template <int ID, int N> __device__ __forceinline__ void bar_arrive() { asm volatile("bar.arrive %0, %1;" :: "n"(ID), "n"(N) : "memory"); }
template <int ID, int N> __device__ __forceinline__ void bar_sync() { asm volatile("bar.sync %0, %1;" :: "n"(ID), "n"(N) : "memory"); }
__device__ __forceinline__ void bar_wg(int wg) { asm volatile("bar.sync %0, 128;" :: "r"(2 + wg) : "memory"); }
__device__ __forceinline__ void cluster_sync() {
  asm volatile("barrier.cluster.arrive.relaxed.aligned;\nbarrier.cluster.wait.aligned;" ::: "memory");
}
__device__ __forceinline__ void cluster_wait() { asm volatile("barrier.cluster.wait.acquire.aligned;" ::: "memory"); }
enum { BAR_X1 = 7, BAR_WF = 8  , BAR_SKEW = 10 };

__device__ __forceinline__ void wgmma_fence() { asm volatile("wgmma.fence.sync.aligned;" ::: "memory"); }
__device__ __forceinline__ void wgmma_commit() { asm volatile("wgmma.commit_group.sync.aligned;" ::: "memory"); }
template <int N> __device__ __forceinline__ void wgmma_wait() { asm volatile("wgmma.wait_group.sync.aligned %0;" :: "n"(N) : "memory"); }

template <int scale_d, int tnsp_b = 1> __device__ __forceinline__ void wgmma_n192(float* d, uint64_t descA, uint64_t descB) {
  asm volatile("{\n.reg .pred p;\nsetp.ne.b32 p, %98, 0;\n"
               "wgmma.mma_async.sync.aligned.m64n192k16.f32.bf16.bf16 {%0,%1,%2,%3,%4,%5,%6,%7,%8,%9,%10,%11,%12,%13,%14,%15,%16,%17,%18,%19,%20,%21,%22,%23,%24,%25,%26,%27,%28,%29,%30,%31,%32,%33,%34,%35,%36,%37,%38,%39,%40,%41,%42,%43,%44,%45,%46,%47,%48,%49,%50,%51,%52,%53,%54,%55,%56,%57,%58,%59,%60,%61,%62,%63,%64,%65,%66,%67,%68,%69,%70,%71,%72,%73,%74,%75,%76,%77,%78,%79,%80,%81,%82,%83,%84,%85,%86,%87,%88,%89,%90,%91,%92,%93,%94,%95}, %96, %97, p, 1, 1, 0, %99;\n}\n"
               : "+f"(d[0]), "+f"(d[1]), "+f"(d[2]), "+f"(d[3]), "+f"(d[4]), "+f"(d[5]), "+f"(d[6]), "+f"(d[7]), "+f"(d[8]), "+f"(d[9]), "+f"(d[10]), "+f"(d[11]), "+f"(d[12]), "+f"(d[13]), "+f"(d[14]), "+f"(d[15]), "+f"(d[16]), "+f"(d[17]), "+f"(d[18]), "+f"(d[19]), "+f"(d[20]), "+f"(d[21]), "+f"(d[22]), "+f"(d[23]), "+f"(d[24]), "+f"(d[25]), "+f"(d[26]), "+f"(d[27]), "+f"(d[28]), "+f"(d[29]), "+f"(d[30]), "+f"(d[31]), "+f"(d[32]), "+f"(d[33]), "+f"(d[34]), "+f"(d[35]), "+f"(d[36]), "+f"(d[37]), "+f"(d[38]), "+f"(d[39]), "+f"(d[40]), "+f"(d[41]), "+f"(d[42]), "+f"(d[43]), "+f"(d[44]), "+f"(d[45]), "+f"(d[46]), "+f"(d[47]), "+f"(d[48]), "+f"(d[49]), "+f"(d[50]), "+f"(d[51]), "+f"(d[52]), "+f"(d[53]), "+f"(d[54]), "+f"(d[55]), "+f"(d[56]), "+f"(d[57]), "+f"(d[58]), "+f"(d[59]), "+f"(d[60]), "+f"(d[61]), "+f"(d[62]), "+f"(d[63]), "+f"(d[64]), "+f"(d[65]), "+f"(d[66]), "+f"(d[67]), "+f"(d[68]), "+f"(d[69]), "+f"(d[70]), "+f"(d[71]), "+f"(d[72]), "+f"(d[73]), "+f"(d[74]), "+f"(d[75]), "+f"(d[76]), "+f"(d[77]), "+f"(d[78]), "+f"(d[79]), "+f"(d[80]), "+f"(d[81]), "+f"(d[82]), "+f"(d[83]), "+f"(d[84]), "+f"(d[85]), "+f"(d[86]), "+f"(d[87]), "+f"(d[88]), "+f"(d[89]), "+f"(d[90]), "+f"(d[91]), "+f"(d[92]), "+f"(d[93]), "+f"(d[94]), "+f"(d[95])
               : "l"(descA), "l"(descB), "n"(scale_d), "n"(tnsp_b));
}
template <int scale_d> __device__ __forceinline__ void wgmma4_n192(float* d, uint32_t da, uint32_t db) {
#define R_ "{%0,%1,%2,%3,%4,%5,%6,%7,%8,%9,%10,%11,%12,%13,%14,%15,%16,%17,%18,%19,%20,%21,%22,%23,%24,%25,%26,%27,%28,%29,%30,%31,%32,%33,%34,%35,%36,%37,%38,%39,%40,%41,%42,%43,%44,%45,%46,%47,%48,%49,%50,%51,%52,%53,%54,%55,%56,%57,%58,%59,%60,%61,%62,%63,%64,%65,%66,%67,%68,%69,%70,%71,%72,%73,%74,%75,%76,%77,%78,%79,%80,%81,%82,%83,%84,%85,%86,%87,%88,%89,%90,%91,%92,%93,%94,%95}"
  asm volatile("{\n.reg .pred p, q;\n.reg .b64 a, b;\nsetp.ne.b32 p, %98, 0;\nsetp.eq.b32 q, 0, 0;\nmov.b64 a, {%96, 0x40000040};\nmov.b64 b, {%97, 0x40000040};\n"
               "wgmma.mma_async.sync.aligned.m64n192k16.f32.bf16.bf16 " R_ ", a, b, p, 1, 1, 0, 1;\nadd.s64 a, a, 2;\nadd.s64 b, b, 128;\n"
               "wgmma.mma_async.sync.aligned.m64n192k16.f32.bf16.bf16 " R_ ", a, b, q, 1, 1, 0, 1;\nadd.s64 a, a, 2;\nadd.s64 b, b, 128;\n"
               "wgmma.mma_async.sync.aligned.m64n192k16.f32.bf16.bf16 " R_ ", a, b, q, 1, 1, 0, 1;\nadd.s64 a, a, 2;\nadd.s64 b, b, 128;\n"
               "wgmma.mma_async.sync.aligned.m64n192k16.f32.bf16.bf16 " R_ ", a, b, q, 1, 1, 0, 1;\n}\n"
               : "+f"(d[0]), "+f"(d[1]), "+f"(d[2]), "+f"(d[3]), "+f"(d[4]), "+f"(d[5]), "+f"(d[6]), "+f"(d[7]), "+f"(d[8]), "+f"(d[9]), "+f"(d[10]), "+f"(d[11]), "+f"(d[12]), "+f"(d[13]), "+f"(d[14]), "+f"(d[15]), "+f"(d[16]), "+f"(d[17]), "+f"(d[18]), "+f"(d[19]), "+f"(d[20]), "+f"(d[21]), "+f"(d[22]), "+f"(d[23]), "+f"(d[24]), "+f"(d[25]), "+f"(d[26]), "+f"(d[27]), "+f"(d[28]), "+f"(d[29]), "+f"(d[30]), "+f"(d[31]), "+f"(d[32]), "+f"(d[33]), "+f"(d[34]), "+f"(d[35]), "+f"(d[36]), "+f"(d[37]), "+f"(d[38]), "+f"(d[39]), "+f"(d[40]), "+f"(d[41]), "+f"(d[42]), "+f"(d[43]), "+f"(d[44]), "+f"(d[45]), "+f"(d[46]), "+f"(d[47]), "+f"(d[48]), "+f"(d[49]), "+f"(d[50]), "+f"(d[51]), "+f"(d[52]), "+f"(d[53]), "+f"(d[54]), "+f"(d[55]), "+f"(d[56]), "+f"(d[57]), "+f"(d[58]), "+f"(d[59]), "+f"(d[60]), "+f"(d[61]), "+f"(d[62]), "+f"(d[63]), "+f"(d[64]), "+f"(d[65]), "+f"(d[66]), "+f"(d[67]), "+f"(d[68]), "+f"(d[69]), "+f"(d[70]), "+f"(d[71]), "+f"(d[72]), "+f"(d[73]), "+f"(d[74]), "+f"(d[75]), "+f"(d[76]), "+f"(d[77]), "+f"(d[78]), "+f"(d[79]), "+f"(d[80]), "+f"(d[81]), "+f"(d[82]), "+f"(d[83]), "+f"(d[84]), "+f"(d[85]), "+f"(d[86]), "+f"(d[87]), "+f"(d[88]), "+f"(d[89]), "+f"(d[90]), "+f"(d[91]), "+f"(d[92]), "+f"(d[93]), "+f"(d[94]), "+f"(d[95])
               : "r"(da), "r"(db), "n"(scale_d));
#undef R_
}
template <int scale_d> __device__ __forceinline__ void wgmma4_n128(float* d, uint32_t da, uint32_t db) {
#define R_ "{%0,%1,%2,%3,%4,%5,%6,%7,%8,%9,%10,%11,%12,%13,%14,%15,%16,%17,%18,%19,%20,%21,%22,%23,%24,%25,%26,%27,%28,%29,%30,%31,%32,%33,%34,%35,%36,%37,%38,%39,%40,%41,%42,%43,%44,%45,%46,%47,%48,%49,%50,%51,%52,%53,%54,%55,%56,%57,%58,%59,%60,%61,%62,%63}"
  asm volatile("{\n.reg .pred p, q;\n.reg .b64 a, b;\nsetp.ne.b32 p, %66, 0;\nsetp.eq.b32 q, 0, 0;\nmov.b64 a, {%64, 0x40000040};\nmov.b64 b, {%65, 0x40000040};\n"
               "wgmma.mma_async.sync.aligned.m64n128k16.f32.bf16.bf16 " R_ ", a, b, p, 1, 1, 0, 1;\nadd.s64 a, a, 2;\nadd.s64 b, b, 128;\n"
               "wgmma.mma_async.sync.aligned.m64n128k16.f32.bf16.bf16 " R_ ", a, b, q, 1, 1, 0, 1;\nadd.s64 a, a, 2;\nadd.s64 b, b, 128;\n"
               "wgmma.mma_async.sync.aligned.m64n128k16.f32.bf16.bf16 " R_ ", a, b, q, 1, 1, 0, 1;\nadd.s64 a, a, 2;\nadd.s64 b, b, 128;\n"
               "wgmma.mma_async.sync.aligned.m64n128k16.f32.bf16.bf16 " R_ ", a, b, q, 1, 1, 0, 1;\n}\n"
               : "+f"(d[0]), "+f"(d[1]), "+f"(d[2]), "+f"(d[3]), "+f"(d[4]), "+f"(d[5]), "+f"(d[6]), "+f"(d[7]), "+f"(d[8]), "+f"(d[9]), "+f"(d[10]), "+f"(d[11]), "+f"(d[12]), "+f"(d[13]), "+f"(d[14]), "+f"(d[15]), "+f"(d[16]), "+f"(d[17]), "+f"(d[18]), "+f"(d[19]), "+f"(d[20]), "+f"(d[21]), "+f"(d[22]), "+f"(d[23]), "+f"(d[24]), "+f"(d[25]), "+f"(d[26]), "+f"(d[27]), "+f"(d[28]), "+f"(d[29]), "+f"(d[30]), "+f"(d[31]), "+f"(d[32]), "+f"(d[33]), "+f"(d[34]), "+f"(d[35]), "+f"(d[36]), "+f"(d[37]), "+f"(d[38]), "+f"(d[39]), "+f"(d[40]), "+f"(d[41]), "+f"(d[42]), "+f"(d[43]), "+f"(d[44]), "+f"(d[45]), "+f"(d[46]), "+f"(d[47]), "+f"(d[48]), "+f"(d[49]), "+f"(d[50]), "+f"(d[51]), "+f"(d[52]), "+f"(d[53]), "+f"(d[54]), "+f"(d[55]), "+f"(d[56]), "+f"(d[57]), "+f"(d[58]), "+f"(d[59]), "+f"(d[60]), "+f"(d[61]), "+f"(d[62]), "+f"(d[63])
               : "r"(da), "r"(db), "n"(scale_d));
#undef R_
}
template <int scale_d> __device__ __forceinline__ void wgmma_n32(float* d, uint64_t descA, uint64_t descB) {
  asm volatile("{\n.reg .pred p;\nsetp.ne.b32 p, %18, 0;\n"
               "wgmma.mma_async.sync.aligned.m64n32k16.f32.bf16.bf16 {%0,%1,%2,%3,%4,%5,%6,%7,%8,%9,%10,%11,%12,%13,%14,%15}, %16, %17, p, 1, 1, 0, 1;\n}\n"
               : "+f"(d[0]), "+f"(d[1]), "+f"(d[2]), "+f"(d[3]), "+f"(d[4]), "+f"(d[5]), "+f"(d[6]), "+f"(d[7]), "+f"(d[8]), "+f"(d[9]), "+f"(d[10]), "+f"(d[11]), "+f"(d[12]), "+f"(d[13]), "+f"(d[14]), "+f"(d[15])
               : "l"(descA), "l"(descB), "n"(scale_d));
}
template <int scale_d, int tnsp_a> __device__ __forceinline__ void wgmma_n40(float* d, uint64_t descA, uint64_t descB) {
  asm volatile("{\n.reg .pred p;\nsetp.ne.b32 p, %22, 0;\n"
               "wgmma.mma_async.sync.aligned.m64n40k16.f32.bf16.bf16 {%0,%1,%2,%3,%4,%5,%6,%7,%8,%9,%10,%11,%12,%13,%14,%15,%16,%17,%18,%19}, %20, %21, p, 1, 1, %23, 1;\n}\n"
               : "+f"(d[0]), "+f"(d[1]), "+f"(d[2]), "+f"(d[3]), "+f"(d[4]), "+f"(d[5]), "+f"(d[6]), "+f"(d[7]), "+f"(d[8]), "+f"(d[9]), "+f"(d[10]), "+f"(d[11]), "+f"(d[12]), "+f"(d[13]), "+f"(d[14]), "+f"(d[15]), "+f"(d[16]), "+f"(d[17]), "+f"(d[18]), "+f"(d[19])
               : "l"(descA), "l"(descB), "n"(scale_d), "n"(tnsp_a));
}
template <int scale_d> __device__ __forceinline__ void wgmma_n40_rs(float* d, const uint32_t* a, uint64_t descB) {
  asm volatile("{\n.reg .pred p;\nsetp.ne.b32 p, %25, 0;\n"
               "wgmma.mma_async.sync.aligned.m64n40k16.f32.bf16.bf16 {%0,%1,%2,%3,%4,%5,%6,%7,%8,%9,%10,%11,%12,%13,%14,%15,%16,%17,%18,%19}, {%20,%21,%22,%23}, %24, p, 1, 1, 1;\n}\n"
               : "+f"(d[0]), "+f"(d[1]), "+f"(d[2]), "+f"(d[3]), "+f"(d[4]), "+f"(d[5]), "+f"(d[6]), "+f"(d[7]), "+f"(d[8]), "+f"(d[9]), "+f"(d[10]), "+f"(d[11]), "+f"(d[12]), "+f"(d[13]), "+f"(d[14]), "+f"(d[15]), "+f"(d[16]), "+f"(d[17]), "+f"(d[18]), "+f"(d[19])
               : "r"(a[0]), "r"(a[1]), "r"(a[2]), "r"(a[3]), "l"(descB), "n"(scale_d));
}
__device__ __forceinline__ void wgmma_copy(float* d, uint32_t da, uint64_t descB, int keep) {
  asm volatile("{\n.reg .pred p;\n.reg .b64 a;\nsetp.ne.b32 p, %66, 0;\nmov.b64 a, {%64, 0x40000040};\n"
               "wgmma.mma_async.sync.aligned.m64n16k16.f32.bf16.bf16 {%0,%1,%2,%3,%4,%5,%6,%7}, a, %65, p, 1, 1, 0, 0;\nadd.s64 a, a, 2;\n"
               "wgmma.mma_async.sync.aligned.m64n16k16.f32.bf16.bf16 {%8,%9,%10,%11,%12,%13,%14,%15}, a, %65, p, 1, 1, 0, 0;\nadd.s64 a, a, 2;\n"
               "wgmma.mma_async.sync.aligned.m64n16k16.f32.bf16.bf16 {%16,%17,%18,%19,%20,%21,%22,%23}, a, %65, p, 1, 1, 0, 0;\nadd.s64 a, a, 2;\n"
               "wgmma.mma_async.sync.aligned.m64n16k16.f32.bf16.bf16 {%24,%25,%26,%27,%28,%29,%30,%31}, a, %65, p, 1, 1, 0, 0;\nadd.s64 a, a, 1018;\n"
               "wgmma.mma_async.sync.aligned.m64n16k16.f32.bf16.bf16 {%32,%33,%34,%35,%36,%37,%38,%39}, a, %65, p, 1, 1, 0, 0;\nadd.s64 a, a, 2;\n"
               "wgmma.mma_async.sync.aligned.m64n16k16.f32.bf16.bf16 {%40,%41,%42,%43,%44,%45,%46,%47}, a, %65, p, 1, 1, 0, 0;\nadd.s64 a, a, 2;\n"
               "wgmma.mma_async.sync.aligned.m64n16k16.f32.bf16.bf16 {%48,%49,%50,%51,%52,%53,%54,%55}, a, %65, p, 1, 1, 0, 0;\nadd.s64 a, a, 2;\n"
               "wgmma.mma_async.sync.aligned.m64n16k16.f32.bf16.bf16 {%56,%57,%58,%59,%60,%61,%62,%63}, a, %65, p, 1, 1, 0, 0;\n"
               "}\n"
               : "+f"(d[0]), "+f"(d[1]), "+f"(d[2]), "+f"(d[3]), "+f"(d[4]), "+f"(d[5]), "+f"(d[6]), "+f"(d[7]), "+f"(d[8]), "+f"(d[9]), "+f"(d[10]), "+f"(d[11]), "+f"(d[12]), "+f"(d[13]), "+f"(d[14]), "+f"(d[15]), "+f"(d[16]), "+f"(d[17]), "+f"(d[18]), "+f"(d[19]), "+f"(d[20]), "+f"(d[21]), "+f"(d[22]), "+f"(d[23]), "+f"(d[24]), "+f"(d[25]), "+f"(d[26]), "+f"(d[27]), "+f"(d[28]), "+f"(d[29]), "+f"(d[30]), "+f"(d[31]), "+f"(d[32]), "+f"(d[33]), "+f"(d[34]), "+f"(d[35]), "+f"(d[36]), "+f"(d[37]), "+f"(d[38]), "+f"(d[39]), "+f"(d[40]), "+f"(d[41]), "+f"(d[42]), "+f"(d[43]), "+f"(d[44]), "+f"(d[45]), "+f"(d[46]), "+f"(d[47]), "+f"(d[48]), "+f"(d[49]), "+f"(d[50]), "+f"(d[51]), "+f"(d[52]), "+f"(d[53]), "+f"(d[54]), "+f"(d[55]), "+f"(d[56]), "+f"(d[57]), "+f"(d[58]), "+f"(d[59]), "+f"(d[60]), "+f"(d[61]), "+f"(d[62]), "+f"(d[63])
               : "r"(da), "l"(descB), "r"(keep));
}
__device__ __forceinline__ uint64_t make_desc(uint32_t addr, uint32_t lbo_bytes, uint32_t sbo_bytes) {
  return (uint64_t)((addr & 0x3FFFF) >> 4) | ((uint64_t)(lbo_bytes >> 4) << 16) | ((uint64_t)(sbo_bytes >> 4) << 32) | (1ull << 62);
}

__device__ __forceinline__ void ldsm_x4(uint32_t addr, uint32_t& r0, uint32_t& r1, uint32_t& r2, uint32_t& r3) {
  asm volatile("ldmatrix.sync.aligned.m8n8.x4.shared.b16 {%0,%1,%2,%3}, [%4];" : "=r"(r0), "=r"(r1), "=r"(r2), "=r"(r3) : "r"(addr) : "memory");
}
__device__ __forceinline__ void ldsm_x4_t(uint32_t addr, uint32_t& r0, uint32_t& r1, uint32_t& r2, uint32_t& r3) {
  asm volatile("ldmatrix.sync.aligned.m8n8.x4.trans.shared.b16 {%0,%1,%2,%3}, [%4];" : "=r"(r0), "=r"(r1), "=r"(r2), "=r"(r3) : "r"(addr) : "memory");
}
__device__ __forceinline__ void stsm_x4(uint32_t addr, uint32_t r0, uint32_t r1, uint32_t r2, uint32_t r3) {
  asm volatile("stmatrix.sync.aligned.m8n8.x4.shared.b16 [%0], {%1,%2,%3,%4};" :: "r"(addr), "r"(r0), "r"(r1), "r"(r2), "r"(r3) : "memory");
}
__device__ __forceinline__ void sts128(uint32_t addr, uint32_t a, uint32_t b, uint32_t c, uint32_t d) {
  asm volatile("st.shared.v4.u32 [%0], {%1,%2,%3,%4};" :: "r"(addr), "r"(a), "r"(b), "r"(c), "r"(d) : "memory");
}
__device__ __forceinline__ float lds32f(uint32_t addr) {
  float v;
  asm volatile("ld.shared.f32 %0, [%1];" : "=f"(v) : "r"(addr) : "memory");
  return v;
}
__device__ __forceinline__ void sts32f(uint32_t addr, float a) {
  asm volatile("st.shared.f32 [%0], %1;" :: "r"(addr), "f"(a) : "memory");
}
__device__ __forceinline__ void mma_bf16(float (&c)[4], uint32_t a0, uint32_t a1, uint32_t a2, uint32_t a3, uint32_t b0, uint32_t b1) {
  asm volatile("mma.sync.aligned.m16n8k16.row.col.f32.bf16.bf16.f32 {%0,%1,%2,%3}, {%4,%5,%6,%7}, {%8,%9}, {%0,%1,%2,%3};"
               : "+f"(c[0]), "+f"(c[1]), "+f"(c[2]), "+f"(c[3]) : "r"(a0), "r"(a1), "r"(a2), "r"(a3), "r"(b0), "r"(b1));
}
__device__ __forceinline__ void mma_bf16_z(float (&c)[4], uint32_t a0, uint32_t a1, uint32_t a2, uint32_t a3, uint32_t b0, uint32_t b1) {
  asm volatile("mma.sync.aligned.m16n8k16.row.col.f32.bf16.bf16.f32 {%0,%1,%2,%3}, {%4,%5,%6,%7}, {%8,%9}, {%10,%10,%10,%10};"
               : "=f"(c[0]), "=f"(c[1]), "=f"(c[2]), "=f"(c[3]) : "r"(a0), "r"(a1), "r"(a2), "r"(a3), "r"(b0), "r"(b1), "f"(0.f));
}
__device__ __forceinline__ uint32_t movm_t(uint32_t v) {
  uint32_t r;
  asm volatile("movmatrix.sync.aligned.m8n8.trans.b16 %0, %1;" : "=r"(r) : "r"(v));
  return r;
}
__device__ __forceinline__ uint32_t pack_bf16(float lo, float hi) {
  uint32_t r;
  asm("cvt.rn.bf16x2.f32 %0, %1, %2;" : "=r"(r) : "f"(hi), "f"(lo));
  return r;
}
__device__ __forceinline__ float bf_lo(uint32_t v) { return __uint_as_float(v << 16); }
__device__ __forceinline__ float bf_hi(uint32_t v) { return __uint_as_float(v & 0xFFFF0000u); }
__device__ __forceinline__ void split3(float x, uint32_t& h, uint32_t& m, uint32_t& l) {
  h = pack_bf16(x, 0.f); x -= bf_lo(h);
  m = pack_bf16(x, 0.f); x -= bf_lo(m);
  l = pack_bf16(x, 0.f);
}
__device__ __forceinline__ float ex2(float x) { float r; asm("ex2.approx.ftz.f32 %0, %1;" : "=f"(r) : "f"(x)); return r; }
__device__ __forceinline__ float rcp_fast(float x) { float r; asm("rcp.approx.ftz.f32 %0, %1;" : "=f"(r) : "f"(x)); return r; }
__device__ __forceinline__ void red_v4(float* p, float a, float b, float c, float d) {
  asm volatile("red.global.add.v4.f32 [%0], {%1, %2, %3, %4};" :: "l"(p), "f"(a), "f"(b), "f"(c), "f"(d) : "memory");
}
__device__ __forceinline__ uint4 ld_ll(const uint4* p) {
  uint4 v;
  asm volatile("{\n.reg .b64 a, b;\nld.relaxed.gpu.global.v2.b64 {a, b}, [%4];\nmov.b64 {%0, %1}, a;\nmov.b64 {%2, %3}, b;\n}\n"
               : "=r"(v.x), "=r"(v.y), "=r"(v.z), "=r"(v.w) : "l"(p) : "memory");
  return v;
}
__device__ __forceinline__ void st_b64(uint2* p, uint32_t a, uint32_t b) {
  asm volatile("{\n.reg .b64 v;\nmov.b64 v, {%1, %2};\nst.relaxed.gpu.global.b64 [%0], v;\n}\n" :: "l"(p), "r"(a), "r"(b) : "memory");
}
__device__ __forceinline__ void st_b128(uint4* p, uint32_t a, uint32_t b, uint32_t c, uint32_t d) {
  asm volatile("{\n.reg .b128 v;\nmov.b128 v, {%1, %2, %3, %4};\nst.relaxed.gpu.global.b128 [%0], v;\n}\n" :: "l"(p), "r"(a), "r"(b), "r"(c), "r"(d) : "memory");
}
__device__ __forceinline__ uint4 ld_b128(const uint4* p) {
  uint4 v;
  asm volatile("{\n.reg .b128 v;\nld.relaxed.gpu.global.b128 v, [%4];\nmov.b128 {%0, %1, %2, %3}, v;\n}\n" : "=r"(v.x), "=r"(v.y), "=r"(v.z), "=r"(v.w) : "l"(p) : "memory");
  return v;
}

constexpr float LOG2E = 1.4426950408889634f;

struct Params {
  const __nv_bfloat16* x0;
  const __nv_bfloat16* wA_qkv;
  const __nv_bfloat16* wA_o;
  const __nv_bfloat16* wB_qkv;
  const __nv_bfloat16* wB_phi;
  const __nv_bfloat16* wB_o;
  __nv_bfloat16* out;
};

#define ACC_DEF(d, n) _Pragma("unroll") for (int i_ = 0; i_ < (n); i_++) asm volatile("" : "=f"(d[i_]))
#define ACC_FENCE(d, n) _Pragma("unroll") for (int i_ = 0; i_ < (n); i_++) asm volatile("" : "+f"(d[i_]) :: "memory")
#define PIN(a, n) _Pragma("unroll") for (int i_ = 0; i_ < (n); i_++) asm volatile("" : "+f"((a)[i_]))
#define PINU(a, n) _Pragma("unroll") for (int i_ = 0; i_ < (n); i_++) asm volatile("" : "+r"((a)[i_]))

#define V_ADDR(p0) uint32_t va_[2] = {(p0) + (srowoff >> 1) + (lhi ^ lsw2), (p0) + (srowoff >> 1) + ((32 + lhi) ^ lsw2)}
#define STAGE_V(acc) { \
    _Pragma("unroll") for (int j_ = 0; j_ < 4; j_++) { \
      const float* a_ = (acc) + j_ * 8; \
      stsm_x4(va_[j_ & 1] + (j_ >> 1) * 8192, \
              pack_bf16(rs0 * a_[0], rs0 * a_[1]), pack_bf16(rs1 * a_[2], rs1 * a_[3]), pack_bf16(rs0 * a_[4], rs0 * a_[5]), pack_bf16(rs1 * a_[6], rs1 * a_[7])); } }
#define FRAG(dst, acc, TR, grp) { \
    _Pragma("unroll") for (int i_ = 0; i_ < 16; i_++) { \
      const float r_ = (i_ & 1) ? rs1 : rs0; \
      const uint32_t w_ = pack_bf16(r_ * (acc)[2 * i_], r_ * (acc)[2 * i_ + 1]); \
      if (TR) (dst)[i_] = movm_t(w_); else (dst)[(i_ & 12) + (i_ & 1) * 2 + ((i_ >> 1) & 1)] = w_; } \
    if (warp == 7 && mm < 15) { \
      _Pragma("unroll") for (int j_ = 0; j_ < 4; j_++) \
        st_b128(g_halo + (size_t)(mm * 8 + jj) * 512 + ((grp) * 4 + j_) * 32 + lane, ((dst)[j_ * 4] & ~1u) | H_BIT(l), (dst)[j_ * 4 + 1], (dst)[j_ * 4 + 2], (dst)[j_ * 4 + 3]); } \
    PINU(dst, 16); }
#define FRAG_PUT(src, slot) if (warp < 7) { _Pragma("unroll") for (int j_ = 0; j_ < 4; j_++) \
      sts128(sbase + (slot) * SLOT + 2048 + warp * 2048 + j_ * 512 + lane * 16, (src)[j_ * 4], (src)[j_ * 4 + 1], (src)[j_ * 4 + 2], (src)[j_ * 4 + 3]); }
#define FRAG_GET(dst, slot) { _Pragma("unroll") for (int j_ = 0; j_ < 4; j_++) \
      asm volatile("ld.shared.v4.u32 {%0, %1, %2, %3}, [%4];" : "=r"((dst)[j_ * 4]), "=r"((dst)[j_ * 4 + 1]), "=r"((dst)[j_ * 4 + 2]), "=r"((dst)[j_ * 4 + 3]) \
                   : "r"(sbase + (slot) * SLOT + warp * 2048 + j_ * 512 + lane * 16) : "memory"); }
#define RW(j) (((j) >> 1) * 4 + ((j) & 1))
template <int POS> __device__ __forceinline__ float exps16_(float* o, const float* p) {
  float s[4];
#pragma unroll
  for (int j = 0; j < 16; j++) { o[j] = ex2(POS ? p[RW(j)] : -p[RW(j)]); if (j < 4) s[j] = o[j]; else s[j & 3] += o[j]; }
  const float r = (s[0] + s[1]) + (s[2] + s[3]);
  return r + __shfl_xor_sync(0xffffffffu, r, 1);
}
template <int POS> __device__ __forceinline__ void exps16_fix(float* o, const float* p, float& sum) {
  if (__builtin_expect(__any_sync(0xffffffffu, !(sum > SUMLO && sum < SUMHI)), 0)) {
    float m = p[0], q[32];
#pragma unroll
    for (int j = 1; j < 16; j++) m = POS ? fmaxf(m, p[RW(j)]) : fminf(m, p[RW(j)]);
    const float x = __shfl_xor_sync(0xffffffffu, m, 1);
    m = POS ? fmaxf(m, x) : fminf(m, x);
#pragma unroll
    for (int j = 0; j < 16; j++) q[RW(j)] = p[RW(j)] - m;
    sum = exps16_<POS>(o, q);
  }
}
__device__ __forceinline__ void store16(const float* e, float sum, uint32_t dst, uint32_t dsw, int c0) {
  const float inv = rcp_fast(sum);
#pragma unroll
  for (int j = 0; j < 2; j++)
    sts128(dst + (((c0 + j) << 4) ^ dsw), pack_bf16(e[j * 8] * inv, e[j * 8 + 1] * inv), pack_bf16(e[j * 8 + 2] * inv, e[j * 8 + 3] * inv),
           pack_bf16(e[j * 8 + 4] * inv, e[j * 8 + 5] * inv), pack_bf16(e[j * 8 + 6] * inv, e[j * 8 + 7] * inv));
}
template <int POS> __device__ __forceinline__ void expp16(uint32_t* o, float* p) {
  {
#pragma unroll
    for (int r = 0; r < 4; r += 2) {
      float m = p[r];
#pragma unroll
      for (int j = 1; j < 8; j++) m = POS ? fmaxf(m, p[r + RW(j)]) : fminf(m, p[r + RW(j)]);
#pragma unroll
      for (int s = 1; s <= 2; s <<= 1) { const float x = __shfl_xor_sync(0xffffffffu, m, s); m = POS ? fmaxf(m, x) : fminf(m, x); }
#pragma unroll
      for (int j = 0; j < 8; j++) p[r + RW(j)] -= m;
    }
  }
#pragma unroll
  for (int j = 0; j < 8; j++) o[j] = pack_bf16(ex2(POS ? p[2 * j] : -p[2 * j]), ex2(POS ? p[2 * j + 1] : -p[2 * j + 1]));
}
__device__ __forceinline__ void scale32(float* o, const float* p, float c0, float c1) {
#pragma unroll
  for (int i = 0; i < 32; i++) asm volatile("mul.f32 %0, %1, %2;" : "=f"(o[i]) : "f"(p[i]), "f"((i & 2) ? c1 : c0));
}
__device__ __forceinline__ bool any_big(const float* p) {
  float m[4];
#pragma unroll
  for (int i = 0; i < 32; i++) m[i >> 3] = (i & 7) ? fmaf(p[i], p[i], m[i >> 3]) : p[i] * p[i];
  return __any_sync(0xffffffffu, !(fmaxf(fmaxf(m[0], m[1]), fmaxf(m[2], m[3])) < BIGLIM));
}
__device__ __forceinline__ void phiq_a(float* p, bool big) {
  if (__builtin_expect(!big, 1)) {
#pragma unroll
    for (int j = 0; j < 16; j++) p[j] = ex2(p[j]);
  }
}
template <int NEXT> __device__ __forceinline__ void phiq_b(uint32_t* o, float* p, bool big) {
  if (__builtin_expect(big, 0)) {
    expp16<0>(o, p); expp16<1>(o + 8, p);
  } else {
    if (NEXT) phiq_a(p + 16, false);
#pragma unroll
    for (int j = 0; j < 4; j++) {
      const float a = p[4 * j], b = p[4 * j + 1], c = p[4 * j + 2], d = p[4 * j + 3];
      const float ab = a * b, cd = c * d, r = rcp_fast(ab * cd), x = r * cd, y = r * ab;
      o[2 * j] = pack_bf16(x * b, x * a); o[2 * j + 1] = pack_bf16(y * d, y * c);
      o[8 + 2 * j] = pack_bf16(a, b); o[9 + 2 * j] = pack_bf16(c, d);
    }
  }
}
#define SCHED_FENCE() asm volatile("pmevent 0;" ::: "memory")

__global__ void __cluster_dims__(2, 1, 1) __launch_bounds__(384, 1)
mega_kernel(const __grid_constant__ CUtensorMap tm_x0, const __grid_constant__ CUtensorMap tm_xo, const __grid_constant__ CUtensorMap tm_os,
            const __grid_constant__ CUtensorMap tm_o, const __grid_constant__ CUtensorMap tm_wf,
            const __grid_constant__ CUtensorMap tm_wqA, const __grid_constant__ CUtensorMap tm_wqB,
            const __grid_constant__ CUtensorMap tm_woA, const __grid_constant__ CUtensorMap tm_woB,
            const __grid_constant__ CUtensorMap tm_phi, const Params prm) {
  extern __shared__ __align__(1024) uint8_t smem_raw[];
  const uint32_t sbase = smem_u32(smem_raw);
  const uint32_t bar_full = sbase + OFF_BAR;
  const uint32_t bar_done = bar_full + 384;
  const uint32_t bar_stat = bar_full + 768, bar_stat2 = bar_full + 776, bar_epi = bar_full + 784, bar_phi = bar_full + 936  , bar_halo = bar_full + 904  ;
  const uint32_t bar_xr = bar_full + 800, bar_lx = bar_full + 808, bar_stg = bar_full + 832;
  const uint32_t bar_chk = bar_full + 848;

  const int warp = __shfl_sync(0xffffffffu, threadIdx.x >> 5, 0), lane = threadIdx.x & 31;
  const uint32_t bar_kx = sbase + OFF_ID + 384 + warp * 8;
  uint32_t rank;
  asm volatile("mov.u32 %0, %%cluster_ctarank;" : "=r"(rank));
  const int aux = (int)blockIdx.x - NMAIN, tp = (int)(blockIdx.x >> 1) - 4;
  const int gp = tp < 0 ? 0 : (tp < 32 ? tp & 7 : 1 + (tp - 32) % 7), me = tp < 0 ? tp + 8 : (tp < 32 ? tp >> 3 : 4 + (tp - 32) / 7);
  const int jj = me, cc = gp;
  const int cta = aux >= 0 ? -1 : (cc * 8 + jj) * 2 + (int)rank;
  const int mm = cc * 2 + (int)rank;

#define LOAD_EPOCH() const unsigned epoch = ld_relaxed(&g_flags.epoch.v), ep1 = epoch + 1; (void)epoch
  int budget = 1 << 22;

  if (cta >= 0) {
    if (warp >= 8 + CPA && warp < 8 + EARLY && elect_one()) {
      const int u = warp - 8;
      const uint32_t fb = bar_full + u * 8;
      mbar_init(fb, 1);
      asm volatile("fence.mbarrier_init.release.cluster;" ::: "memory");
      fence_proxy_async_smem();
      mbar_expect_tx(fb, UPS(u) ? QST : QST + SLOT);
      if (u) __nanosleep(UPS(u) ? STAG1 : STAG2);
      if (!UPS(u)) tma_load_2d(sbase + OFF_S + USL(u) * SLOT, &tm_x0, fb, jj * 128 + USL(u) * 64, mm * 128);
#pragma unroll
      for (int i = 0; i < 6; i++) tma_load_2d(sbase + u * QST + i * 4096, &tm_wqA, fb, jj * 128 + UPS(u) * 64 + (i >> 1) * 1024, jj * 128 + USL(u) * 64 + (i & 1) * 32);
      if (u == 0) PROFT(472);
    }
    __syncwarp();
    {
      const int tx = threadIdx.x;
      const __nv_bfloat16* pf = (tx < 128) ? prm.x0 + (size_t)(mm * 128 + tx) * D_MODEL + jj * 128
                                           : prm.wA_qkv + (size_t)(jj * 128 + (tx & 63)) * 3072 + ((tx - 128) >> 6) * 1024 + jj * 128 + rank * 64;
      if (tx < 320) { if (PF0 && !CPA) asm volatile("prefetch.global.L2 [%0];" :: "l"(pf)); }
      if (PFW && tx < 24 * PFW) {
        const int q = tx % 24;
        asm volatile("prefetch.global.L2 [%0];" :: "l"(prm.wA_qkv + (size_t)(kslice(jj, 2 + tx / 24) * 64 + mm * 4 + q / 6) * 3072 + (q % 6 >> 1) * 1024 + jj * 128 + (q & 1) * 64));
      }
      if (tx == 320) prefetch_tmap(&tm_x0);
      else if (tx == 352) prefetch_tmap(&tm_wqA);
      else if (tx == 383) asm volatile("prefetch.global.L2 [%0];" :: "l"(&g_flags.epoch.v));
    }
    if (elect_one()) {
#pragma unroll
      for (int i = 0; i < 4; i++) {
        const int u = warp * 4 + i;
        if (u >= EARLY || u < CPA) mbar_init(bar_full + u * 8, ((u >= 4 && u < 11) || (u > 32 && u != 40)) ? 2 : 1); mbar_init(bar_done + u * 8, 16);
      }
      mbar_init(bar_stat + warp * 16, 0x111111181182ull >> (4 * warp) & 15);
      mbar_init(bar_stat + warp * 16 + 8, 0x111111121811ull >> (4 * warp) & 15);
      mbar_init(bar_chk + 112 + (warp & 7) * 8, 1);
      if (PAIR) mbar_init(bar_kx, 1);
      asm volatile("fence.mbarrier_init.release.cluster;" ::: "memory");
    }
    __syncwarp();
    __syncthreads();
    asm volatile("barrier.cluster.arrive.relaxed.aligned;" ::: "memory");
  }

  if (cta < 0) {
    LOAD_EPOCH();
    const uint32_t buf = sbase + warp * SLOT, bar = sbase + OFF_BAR + warp * 16;
    const uint32_t lsw = (lane & 7) << 4, lhi = (lane >> 4) << 4, lrow = (lane & 15) * 128;
    const bool el = elect_one();
    if (el) {
      mbar_init(bar, 1); mbar_init(bar + 8, 1);
      asm volatile("fence.mbarrier_init.release.cluster;" ::: "memory");
    }
#pragma unroll 1
    for (int rd = 0; rd < (NLAYERS > 1 ? 5 : 2); rd++) {
      if (rd >= 2 && warp >= 8) break;
      const int tk = rd < 2 ? aux * 12 + warp : aux * 8 + warp;
      const int half = tk & 1;
      const int blk = rd < 2 ? (tk >> 1) * 2 + rd : (4 - rd) * 16 + (tk >> 1);
      const CUtensorMap* tm = rd < 2 ? &tm_wqA : (rd == 2 ? &tm_wqB : &tm_wf);
      const int j0 = (blk & 15) >> 1;
#define AUX_LOAD(n) { const uint32_t d_ = buf + ((n) & 1) * 8192, b_ = bar + ((n) & 1) * 8; const int r_ = kslice(j0, 2 * (n) + half) * 64; \
        mbar_expect_tx(b_, 8192); tma_load_2d(d_, tm, b_, blk * 64, r_); tma_load_2d(d_ + 4096, tm, b_, blk * 64, r_ + 32); }
      if (el) {
        if (rd == 3) { wait_flag(&g_flags.wfready[j0].v, ep1 * 16); fence_proxy_async_global(); }
        AUX_LOAD(0); AUX_LOAD(1);
      }
      __syncwarp();
      float cs[8][4];
#pragma unroll
      for (int i = 0; i < 8; i++) cs[i][0] = cs[i][1] = cs[i][2] = cs[i][3] = 0.f;
#pragma unroll 1
      for (int n = 0; n < 8; n++) {
        const uint32_t tb = buf + (n & 1) * 8192 + lrow;
        mbar_wait(bar + (n & 1) * 8, (n >> 1) & 1);
#pragma unroll
        for (int i = 0; i < 16; i++) {
          uint32_t b0, b1, b2, b3;
          ldsm_x4_t(tb + (i >> 2) * 2048 + (((i & 3) * 32 + lhi) ^ lsw), b0, b1, b2, b3);
          mma_bf16(cs[2 * (i & 3)], 0x3F803F80u, 0x3F803F80u, 0x3F803F80u, 0x3F803F80u, b0, b1);
          mma_bf16(cs[2 * (i & 3) + 1], 0x3F803F80u, 0x3F803F80u, 0x3F803F80u, 0x3F803F80u, b2, b3);
        }
        __syncwarp();
        if (el && n < 6) AUX_LOAD(n + 2);
        __syncwarp();
      }
      if (lane < 4) {
#pragma unroll
        for (int i = 0; i < 8; i++) st_b64(&g_colsum[rd >= 2][blk * 32 + i * 4 + lane][half], __float_as_uint(cs[i][0]), (__float_as_uint(cs[i][1]) & ~3u) | (ep1 & 3));
      }
      __syncwarp();
    }
  } else if (warp >= 8) {
    asm volatile("setmaxnreg.dec.sync.aligned.u32 40;");
    if (warp == 8) {
      const bool el = elect_one();
      cluster_wait();
      if (el) {
#pragma unroll 1
        for (int l = 0; l < NLAYERS; l++) {
          const uint32_t par = l & 1;
          const CUtensorMap* tqk = par ? &tm_wf : &tm_wqA;
          const CUtensorMap* tv = par ? &tm_wqB : &tm_wqA;
          const CUtensorMap* two = par ? &tm_woB : &tm_woA;
          if (l == 1) { LOAD_EPOCH(); wait_flag(&g_flags.wfready[jj].v, ep1 * 16); fence_proxy_async_global(); }
#pragma unroll 1
          for (int u = l ? 0 : EARLY; u < 32; u++) {
            if (u >= 4) mbar_wait_sl(bar_done + (u - 4) * 8, par);
            else if (l) mbar_wait_sl(bar_done + (43 + u + (u >> 1)) * 8, par ^ 1);
            else if (!W23) mbar_wait_sl(bar_full, 0);
            const uint32_t fb = bar_full + u * 8;
            const bool res = u < 11 || (u >= 18 && u < 22);
            mbar_expect_tx(fb, res ? QST : QST + SLOT);
            const int row = kslice(jj, u < 4 ? USL(u) : (u < 18 ? u - 2 : (u < 22 ? u - 6 : u - 20))) * 64 + (int)rank * 32;
            const int ps = u < 4 ? UPS(u) : (u >= 18), col = jj * 128 + ps * 64;
            const int c0 = par ? jj * 128 + (ps ? 0 : 1024) : col;
            const uint32_t dst = sbase + (u & 3) * QST + rank * 4096;
            tma_load_2d_mc(dst, tqk, fb, c0, row);
            tma_load_2d_mc(dst + 8192, tqk, fb, c0 + (par ? 64 : 1024), row);
            tma_load_2d_mc(dst + 16384, tv, fb, col + 2048, row);
            if (l == PRL && u >= PRU && u < PRU + 4) PROFT(473 + u - PRU);
          }
#pragma unroll 1
          for (int s = 0; s < 16; s++) {
            if (s < 5) { if (s != 2 && s != 4) mbar_wait_sl(bar_done + (28 + s) * 8, par); }
            else if (s != 14) mbar_wait_sl(bar_done + (27 + s - (s == 15)) * 8, par);
            const uint32_t fb = bar_full + (32 + s) * 8;
            mbar_expect_tx(fb, SLOT);
            tma_load_2d_mc(sbase + rank * 8192 + (uint32_t)((WO_BSLOT >> (4 * s)) & 15) * SLOT, two, fb, jj * 128 + (int)rank * 64, wslice(jj, s) * 64);
            const int ts = s + par;
            if (s >= 5 && ts < 8) {
              mbar_expect_tx(bar_chk - 8 + ts * 8, SLOT);
              tma_load_2d(sbase + (uint32_t)((WO_ASLOT(par) >> (4 * ts)) & 15) * SLOT, &tm_o, bar_chk - 8 + ts * 8, wslice(jj, ts) * 64, mm * 128);
            }
          }
        }
      }
      __syncwarp();
    } else if (warp == 9) {
      const bool el = elect_one();
      LOAD_EPOCH();
#pragma unroll 1
      for (int lp = 0; lp < 4 * NLAYERS; lp++) {
        const int l = lp >> 2, ph = lp & 3;
        if (ph == 3) continue;
        const uint32_t par = l & 1;
        const unsigned* pp = reinterpret_cast<const unsigned*>(g_obuf + (ph >> 1) * 64 + (size_t)(mm * 128 + (ph ? 0 : S_LEN) + (lane & 7) * 16 + (jj & 1) * 8) * D_MODEL +
                                                               (jj >> 1) * 16 + srcb(jj, lane >> 3) * 128);
        const CUtensorMap* tm = lp ? &tm_o : &tm_x0;
        const int row = mm * 128 + ((ph || !l) ? 0 : S_LEN);
        const uint32_t bit = ph ? O_BIT(l) : X_BIT(l - 1);
        const uint32_t slots = ph ? (uint32_t)(WO_ASLOT(par) >> (ph * 32 - 28)) : 0x8769876u;
        const unsigned long long fr = ph == 0 ? XPACE : ph == 1 ? (par ? 0x353535351Full : 0x35351F1Eull) : (par ? 0x27262524232232ull : 0x27262524233232ull);
        uint32_t no = (lp == 0 || (lp & 7) == 1) ? 0 : ~0u, v0 = 0, v1 = 0;
        if (lp || !AX) mbar_wait_sl(ph ? bar_done + ((uint32_t)fr & 63) * 8 : (l ? bar_done + 47 * 8 : bar_full), ph ? par : (l ? par ^ 1 : 0));
        if (el && ph) PROFT(324 + l * 16 + ph);
        __syncwarp();
        if (no) { v0 = ld_relaxed(pp); __nanosleep(POLLGAP); v1 = ld_relaxed(pp); }
#pragma unroll 1
        for (int i = 0; i < (ph == 1 ? 4 + par : 7); i++, no >>= 8) {
#pragma unroll 1
          for (int it = 0; (no & 0xFF) && it < (1 << 18); it++) {
            no &= __ballot_sync(0xffffffffu, (v0 ^ bit) & 1) >> (8 * i);
            if (no) v0 = ld_relaxed(pp);
            if (!(no & 0xFF)) break;
            no &= __ballot_sync(0xffffffffu, (v1 ^ bit) & 1) >> (8 * i);
            if (no) v1 = ld_relaxed(pp);
          }
          if (ph || i >= XP0) mbar_wait_sl(bar_done + ((uint32_t)(fr >> (8 * i)) & 63) * 8, par);
          if (el) {
            if (i == 0) PROFT(320 + l * 16 + ph);
            const uint32_t cb = (lp ? bar_chk + (ph >> 1) * 112 : bar_full + 32) + i * 8;
            mbar_expect_tx(cb, SLOT);
            tma_load_2d(sbase + ((slots >> (4 * i)) & 15) * SLOT, tm, cb, srcb(jj, i) * 128 + (ph >> 1) * 64, row);
          }
          __syncwarp();
        }
        if (ph == 0 && el) {
          if (l) { wait_flag(&g_flags.xready[l][mm].v, ep1 * 8); fence_proxy_async_global(); }
#pragma unroll 1
          for (int u = 11; u < 34; u++) {
            if (u == 18) u = 22;
            mbar_wait_sl(bar_done + (u - 4) * 8, par);
            if (u == 32) mbar_expect_tx(bar_xr, 2 * SLOT);
            tma_load_2d(sbase + OFF_RA + (u & 3) * SLOT, tm, u < 32 ? bar_full + u * 8 : bar_xr, kslice(jj, u < 18 ? u - 2 : (u < 32 ? u - 20 : u - 32)) * 64, row);
          }
        }
        __syncwarp();
      }
      if (el && atomicAdd(&g_flags.done.v, 1) == ep1 * NMAIN - 1) asm volatile("st.relaxed.gpu.global.u32 [%0], %1;" :: "l"(&g_flags.epoch.v), "r"(ep1) : "memory");
      __syncwarp();
      cluster_wait();
    } else {
      const int hw = warp - 10;
      LOAD_EPOCH();
      const bool el = elect_one();
      cluster_wait();
      if (hw == 0) {
        mbar_wait_sl(bar_full + 8 + 8 * ORD, 0);
        if (lane < 7) prefetch_tmap(lane == 0 ? &tm_os : lane == 1 ? &tm_o : lane == 2 ? &tm_wf : lane == 3 ? &tm_wqB : lane == 4 ? &tm_woA : lane == 5 ? &tm_woB : &tm_phi);
#pragma unroll 1
        for (int i = 0; i < (NLAYERS > 1 ? 9 : 0); i++) {
          if (i == 0 || i == 5) mbar_wait_sl(bar_done + (i ? FD1 : FD0) * 8, 0);
          if (el) {
            if (i == 0) { mbar_expect_tx(bar_phi, 2 * SLOT + 8192); tma_load_2d(sbase + OFF_PHI, &tm_phi, bar_phi, 0, jj * 128); }
            else tma_load_2d(sbase + (i > 4 ? 10 : 12) * SLOT - 4096 + i * 4096, &tm_wqB, bar_phi, (i > 4 ? 896 : 0) + jj * 128 + ((i - 1) >> 1) * 64, mm * 64 + (~i & 1) * 32);
          }
          __syncwarp();
          __nanosleep(PFGAP);
        }
      } else {
        if (XMMA && lane < 24) {
          const uint32_t one = (lane & 8) ? 0u : 0x3F80u << ((lane & 1) * 16), w = (lane >> 1) & 3;
          sts128(sbase + OFF_ID + lane * 16, w == 0 ? one : 0u, w == 1 ? one : 0u, w == 2 ? one : 0u, w == 3 ? one : 0u);
        }
#pragma unroll 1
        for (int b = 0; b < 2; b++) {
          float4* z = reinterpret_cast<float4*>(g_kv[b] + (jj * 4) * KVH + mm * (4 * KVH / 16)) + lane;
#pragma unroll
          for (int i = 0; i < 6; i++) z[i * 32] = make_float4(0.f, 0.f, 0.f, 0.f);
        }
#pragma unroll 1
        for (int i = 0; i < 16; i++) {
          const int b = i >> 2;
          const uint32_t v = (b == 0 ? O_BIT(0) : b == 1 ? X_BIT(0) : H_BIT(0)) + 1;
          uint4* p = b < 2 ? reinterpret_cast<uint4*>(g_obuf + (size_t)(b * S_LEN + mm * 128 + (i & 3) * 32 + (lane >> 3) * 8) * D_MODEL + jj * 128 + (b ? 0 : 64)) + (lane & 7)
                           : g_halo + (size_t)(mm * 8 + jj) * 512 + i * 32 + lane;
          *p = make_uint4(v, v, v, v);
        }
        fence_proxy_async_global();
      }
      __syncwarp();
      uint32_t chkp = 0;
#pragma unroll 1
      for (int lp = hw; lp < 8 * NLAYERS; lp++) {
        const int l = lp >> 3, tk = lp & 7, ph = tk ? 2 - hw : 0;
        const uint32_t par = l & 1;
        int lane; asm volatile("mov.u32 %0, %%laneid;" : "=r"(lane));
        if (tk == 5 || (hw && tk == 0)) {
          const uint32_t bit = ph ? O_BIT(l) : X_BIT(l - 1);
          uint32_t slots = ph ? (uint32_t)(WO_ASLOT(par) >> (ph * 32 - 28)) : 0x8769876u;
          const uint32_t a0 = sbase + (lane & 7) * 126 + lane * 4 + (lane & 1) * 14;
#pragma unroll 1
          for (int c = 0; c < 7; c++, slots >>= 4) {
            const uint32_t cb = bar_chk + 112 - hw * 112 + c * 8;
#pragma unroll 1
            for (int it = 0; it < (1 << 12); it++) {
              mbar_wait_sl(cb, (chkp >> c) & 1);
              chkp ^= 1u << c;
              if (el && c == 0) PROFT(ph == 1 ? 480 + l * 2 : 488 + l * 2 + (ph >> 1));
              uint32_t bad;
              asm volatile("{\n.reg .b32 w<16>;\n"
                           "ld.shared.u32 w0, [%1 + 0];\n"
                           "ld.shared.u32 w1, [%1 + 1024];\n"
                           "ld.shared.u32 w2, [%1 + 2048];\n"
                           "ld.shared.u32 w3, [%1 + 3072];\n"
                           "ld.shared.u32 w4, [%1 + 4096];\n"
                           "ld.shared.u32 w5, [%1 + 5120];\n"
                           "ld.shared.u32 w6, [%1 + 6144];\n"
                           "ld.shared.u32 w7, [%1 + 7168];\n"
                           "ld.shared.u32 w8, [%1 + 8192];\n"
                           "ld.shared.u32 w9, [%1 + 9216];\n"
                           "ld.shared.u32 w10, [%1 + 10240];\n"
                           "ld.shared.u32 w11, [%1 + 11264];\n"
                           "ld.shared.u32 w12, [%1 + 12288];\n"
                           "ld.shared.u32 w13, [%1 + 13312];\n"
                           "ld.shared.u32 w14, [%1 + 14336];\n"
                           "ld.shared.u32 w15, [%1 + 15360];\n"
                           "lop3.b32 w0, w0, w1, %2, 0x7E;\n"
                           "lop3.b32 w2, w2, w3, %2, 0x7E;\n"
                           "lop3.b32 w4, w4, w5, %2, 0x7E;\n"
                           "lop3.b32 w6, w6, w7, %2, 0x7E;\n"
                           "lop3.b32 w8, w8, w9, %2, 0x7E;\n"
                           "lop3.b32 w10, w10, w11, %2, 0x7E;\n"
                           "lop3.b32 w12, w12, w13, %2, 0x7E;\n"
                           "lop3.b32 w14, w14, w15, %2, 0x7E;\n"
                           "lop3.b32 w0, w0, w2, w4, 0xFE;\nlop3.b32 w6, w6, w8, w10, 0xFE;\nlop3.b32 w0, w0, w12, w14, 0xFE;\nlop3.b32 %0, w0, w6, 1, 0xA8;\n}\n"
                           : "=r"(bad) : "r"(a0 + (slots & 15) * SLOT), "r"(bit) : "memory");
              if (__all_sync(0xffffffffu, bad == 0)) break;
              if (el) {
                fence_proxy_async_smem();
                mbar_expect_tx(cb, SLOT);
                tma_load_2d(sbase + (slots & 15) * SLOT, &tm_o, cb, srcb(jj, c) * 128 + (ph >> 1) * 64, mm * 128 + (ph ? 0 : S_LEN));
                RETRY_COUNT();
              }
              __syncwarp();
            }
            if (el) { mbar_arrive_local(bar_full + (c + (ph ? 25 + ph * 8 : 4)) * 8); if (lp == PRL * 8 && c == 0) PROFT(477); }
            __syncwarp();
          }
        } else if (hw && (tk & 5) == 1) {
          {
            const int hp = tk >> 1;
            const uint4* src = reinterpret_cast<const uint4*>(g_colsum[par][jj * 64 + hp * 32 + lane]);
            uint32_t bad;
            int it = 0;
            float c[6];
            do {
              bad = 0;
#pragma unroll
              for (int p = 0; p < 3; p++) {
                const uint4 v = ld_ll(src + ((par && p < 2) ? (hp ? -32 : 512) + p * 32 : p * 512));
                bad |= (v.y ^ ep1) | (v.w ^ ep1);
                c[2 * p] = __uint_as_float(v.x) + __uint_as_float(v.z); c[2 * p + 1] = __uint_as_float(v.y) + __uint_as_float(v.w);
              }
              bad &= 3;
              if (bad) __nanosleep(300);
            } while (bad && ++it < (1 << 16));
#pragma unroll
            for (int p = 0; p < 6; p++) {
              uint32_t h, m, lo;
              split3(c[p], h, m, lo);
              sts128(sbase + OFF_LNB + hp * 4096 + (p >> 1) * 1024 + lane * 32 + (p & 1) * 16, h | (m << 16), h | (lo << 16), h | (m << 16), lo | (m << 16));
            }
            fence_proxy_async_smem();
            __syncwarp();
            if (el) { mbar_arrive_local(hp ? bar_stat2 : bar_stat); if (hp == 0) PROFT(324 + l * 16); }
            __syncwarp();
          }
        } else if (tk == 0) {
          mbar_wait_sl(bar_done + 24, par);
          const uint4* sp = reinterpret_cast<const uint4*>(g_stats + (size_t)(mm * 128) * 8) + lane;
#pragma unroll 1
          for (int hf = 0; hf < 4; hf++) {
            uint4 v[4];
            uint32_t bad;
            int it = 0;
            do {
              bad = 0;
#pragma unroll
              for (int i = 0; i < 4; i++) { v[i] = ld_ll(sp + (hf * 4 + i) * 32); bad |= (v[i].y ^ STAT_TAG(l)) | (v[i].w ^ STAT_TAG(l)); }
              bad &= 3;
              if (bad) __nanosleep(200);
            } while (bad && ++it < (1 << 16));
            __syncwarp();
            float mean = 0.f, m2 = 0.f;
#pragma unroll
            for (int i = 0; i < 4; i++) {
              float a = __uint_as_float(v[i].x) + __uint_as_float(v[i].z);
              a += __shfl_xor_sync(0xffffffffu, a, 1); a += __shfl_xor_sync(0xffffffffu, a, 2);
              a *= 0.125f;
              const float e0 = __uint_as_float(v[i].x) - a, e1 = __uint_as_float(v[i].z) - a;
              float q = fmaf(fmaf(e0, e0, e1 * e1), 128.f, __uint_as_float(v[i].y) + __uint_as_float(v[i].w));
              q += __shfl_xor_sync(0xffffffffu, q, 1); q += __shfl_xor_sync(0xffffffffu, q, 2);
              if ((lane & 3) == i) { mean = a; m2 = q; }
            }
            const uint32_t row = hf * 32 + (lane & 3) * 8 + (lane >> 2);
            uint32_t h, m, lo;
            split3(-0.5f * mean, h, m, lo);
            sts128(sbase + OFF_LNA + row * 16, h | (h << 16), m | (h << 16), lo | (m << 16), m | (lo << 16));
            sts32f(sbase + OFF_ST + row * 4, rsqrtf(m2 * (1.f / 1024.f) + 1e-5f));
          }
          fence_proxy_async_smem();
          __syncwarp();
          if (el) { mbar_arrive_local(bar_stat); PROFT(323 + l * 16); }
          __syncwarp();
#pragma unroll 1
          for (int i = 0; i < 8 - 4 * l; i++) {
            asm volatile("prefetch.global.L2 [%0];" :: "l"(i < 4 ? (l ? prm.wB_o : prm.wA_o) + (size_t)cta * 8192 + i * 2048 + lane * 64
                                                                 : prm.wB_qkv + (size_t)(cta * 8 + (i - 4) * 2 + (lane >> 4)) * 3072 + 2048 + (lane & 15) * 64));
            __nanosleep(PFGAP);
          }
        } else if (lp == 3) {
#pragma unroll 1
          for (int c = 0; c < (NLAYERS > 1 ? 8 : 0); c++) {
            if (!(c & 3)) asm volatile("bar.sync %0, 288;" :: "r"(BAR_WF + (c >> 2)) : "memory");
            if (el) {
              tma_store_2d(&tm_wf, sbase + 11 * SLOT + c * 4096, (c < 4 ? 1024 : -128) + jj * 128 + (c >> 1) * 64, mm * 64 + (c & 1) * 32);
              if ((c & 3) == 3) {
                asm volatile("cp.async.bulk.commit_group;\ncp.async.bulk.wait_group.read 0;" ::: "memory");
                mbar_arrive_local(bar_phi + (c >> 2) * 8);
              } else __nanosleep(WFGAP);
            }
            __syncwarp();
          }
          if (el) { bulk_commit_wait(); signal_release(&g_flags.wfready[jj].v); PROFT(335); }
          __syncwarp();
        } else if (tk == 2 || tk == 4) {
          if (par) continue;
          const int i = tk >> 2;
          mbar_wait_sl(bar_done + (i ? HW1 : (hw ? 19 : HW0)) * 8, 0);
          const uint4* src = g_halo + (size_t)(mm * 8 + jj - 8) * 512 + i * 256 + hw * 128 + lane;
          uint4 v[4];
          int it = 0;
          bool ok;
          do {
#pragma unroll
            for (int j = 0; j < 4; j++) v[j] = mm ? ld_b128(src + j * 32) : make_uint4(H_BIT(l), 0, 0, 0);
            ok = __all_sync(0xffffffffu, (((v[0].x ^ H_BIT(l)) | (v[1].x ^ H_BIT(l)) | (v[2].x ^ H_BIT(l)) | (v[3].x ^ H_BIT(l))) & 1) == 0);
          } while (!ok && ++it < (1 << 16));
          if (lp + hw == 3 && NLAYERS > 1) mbar_wait_sl(bar_phi, 1);
#pragma unroll
          for (int j = 0; j < 4; j++) sts128(sbase + OFF_S + hw * SLOT + j * 512 + lane * 16, v[j].x, v[j].y, v[j].z, v[j].w);
          __syncwarp();
          if (el) { mbar_arrive_local(bar_halo + hw * 8); PROFT(331 + l * 16 + i * 2 + hw); }
          __syncwarp();
        } else if (tk == 6 && hw == 0 && l < NLAYERS - 1) {
          bar_sync<BAR_X1, 288>();
          if (el) {
            PROFT(328 + l * 16);
            mbar_wait_sl(bar_full + XD * 8, par ^ 1);
            tma_store_2d(&tm_o, sbase + 11 * SLOT, jj * 128 + 64, mm * 128 + S_LEN);
            bulk_commit_wait();
            signal_release(&g_flags.xready[l + 1][mm].v);
            PROFT(330 + l * 16);
          }
          __syncwarp();
        }
      }
    }
    cluster_sync();
  } else {
    asm volatile("setmaxnreg.inc.sync.aligned.u32 232;");
    const int wg = warp >> 2;
    const int r0 = warp * 16;
    const uint32_t pK = sbase + OFF_S, pV = sbase + OFF_S + SLOT;
#define PMASKS(on, bit) const uint32_t pm0 = ((on) && t == (g >> 1)), pbit = (bit)
#define PBIT0(w) (((w) & ~pm0) | (pbit & pm0))
#define PBIT1(w) (w)
#define LANE_CONSTS() \
    int lane; asm volatile("mov.u32 %0, %%laneid;" : "=r"(lane)); \
    const int g = lane >> 2, t = lane & 3; \
    const uint32_t srowoff = (r0 + (lane & 15)) * 128, lsw = (lane & 7) << 4, lhi = (lane >> 4) << 4, lsw2 = (lane & 6) << 3; \
    (void)g; (void)t; (void)srowoff; (void)lsw; (void)lhi; (void)lsw2;
    uint32_t stgp = 0, peer;
    asm volatile("mapa.shared::cluster.u32 %0, %1, %2;" : "=r"(peer) : "r"(sbase), "r"(rank ^ 1));
    peer -= sbase;
    const uint32_t dA0 = (((sbase & 0x3FFFF) + wg * 8192) >> 4) | 0x10000u, dB0 = ((sbase & 0x3FFFF) >> 4) | 0x2000000u;
    cluster_wait();
#define DESC(lo, hi) ((uint64_t)(uint32_t)(lo) | ((uint64_t)(hi) << 32))
#define STG_ARRIVE() { __syncwarp(); if (elect_one()) mbar_arrive_local(bar_stg); }
#define STG_WAIT() { mbar_wait(bar_stg, stgp); stgp ^= 1; }
#define PROFS() do {} while (0)
#define REL(addr) { if (elect_one()) { mbar_arrive_local(addr); asm volatile("mbarrier.arrive.shared::cluster.b64 _, [%0];" :: "r"((addr) + peer) : "memory"); } }
#define QSTEP(ACC, DA, SC, PRE) { \
      const uint32_t da = (DA), db = dB0 + (ub & 0x18) * (QST >> 7); \
      mbar_wait(ub, par); \
      PRE; \
      wgmma_fence(); \
      wgmma4_n192<SC>(ACC, da, db); \
      wgmma_commit(); PROFS(); }
#define QREL() { wgmma_wait<1>(); REL(ub + 376); ub += 8; }
#define RA_CUR (dA0 + (OFF_RA >> 4) + (ub & 0x18) * (SLOT >> 7))
#define PUMP1() { QSTEP(S1, RA_CUR, 1, {}); QREL(); }
#define PUMP0() { PUMP1(); SCHED_FENCE(); }
#define PUMP() if (h == 0) PUMP1()
#define WSTEP() { \
      const uint32_t s4 = (ub - bar_full - 256) >> 1; \
      const uint32_t da = dA0 + (((uint32_t)(WO_ASLOT(par) >> s4) & 15) << 10), db = dB0 + (((uint32_t)(WO_BSLOT >> s4) & 15) << 10); \
      mbar_wait(ub, par); \
      wgmma_fence(); \
      wgmma4_n128<1>(S1, da, db); \
      wgmma_commit(); PROFS(); \
      wgmma_wait<1>(); \
      if (s4) REL(ub + 376); \
      ub += 8; }
#define PUMPS(n) { _Pragma("unroll 1") for (int i_ = 0; i_ < (n); i_++) PUMP1(); }
#define SITE(n) { if ((BMASK >> (n)) & 1) PUMP1(); SCHED_FENCE(); }
#define LNSTEP(ACC, hh) { wgmma_fence(); wgmma_n192<1, 0>(ACC, make_desc(sbase + OFF_LNA + wg * 1024, 0, 128) ^ (1ull << 62), make_desc(sbase + OFF_LNB + (hh) * 4096, 0, 128) ^ (1ull << 62)); }
#define WARP_STORE(tm, tile, col, row) { fence_proxy_async_smem(); __syncwarp(); \
      if (elect_one()) { tma_store_2d(tm, (tile) + r0 * 128, col, (row) + r0); asm volatile("cp.async.bulk.commit_group;" ::: "memory"); } __syncwarp(); }
#define PUBLISH_O() WARP_STORE(&tm_os, pO, jj * 128 + h * 64, mm * 128)
#define TILE_CONSTS(base, on, bit) \
      uint32_t ta[5]; \
      { PMASKS(on, bit); (void)pbit; ta[4] = pm0; } \
      _Pragma("unroll") for (int j = 0; j < 4; j++) ta[j] = (base) + srowoff + ((((uint32_t)j << 5) + lhi) ^ lsw); \
      PINU(ta, 5); SCHED_FENCE(); \
      const uint32_t pm0 = ta[4], pbit = (bit)
#define X_OUT(pc, W) { \
      _Pragma("unroll") for (int j = 0; j < 4; j++) \
        stsm_x4(ta[j] + (pc) * SLOT, \
                PBIT0(pack_bf16((W)[j * 8 + 0], (W)[j * 8 + 1])), PBIT0(pack_bf16((W)[j * 8 + 2], (W)[j * 8 + 3])), \
                PBIT1(pack_bf16((W)[j * 8 + 4], (W)[j * 8 + 5])), PBIT1(pack_bf16((W)[j * 8 + 6], (W)[j * 8 + 7]))); }
#define REST_P1(SKEW) { \
      mbar_wait(bar_stat2, par); \
      LNSTEP(S1, 1); \
      _Pragma("unroll 1") while (ub < bar_full + 256) { \
        if (ub == bar_full + 256 - 8 * (SKEW) && wg == 0) bar_sync<BAR_SKEW, 256>(); \
        QSTEP(S1, RA_CUR, 1, {}); \
        if (ub == bar_full + 248 && wg == 1) bar_arrive<BAR_SKEW, 256>(); \
        QREL(); \
      } \
      mbar_wait(bar_done + (31 - (SKEW)) * 8, par);        \
      wgmma_wait<0>(); \
      ACC_FENCE(S1, 96); \
      REL(bar_done + 31 * 8); \
      PROF(13); }
#define FOLD(tile, rd) { \
          LANE_CONSTS(); \
          float d[32]; \
          ACC_DEF(d, 32); \
          mbar_wait(bar_phi, 0); \
          wgmma_fence(); \
          _Pragma("unroll") for (int i = 0; i < 2; i++) { \
            const uint64_t da = make_desc((tile) + wg * 8192 + i * 64, 16, 1024); \
            const uint64_t db = make_desc(sbase + OFF_PHI + wg * 4096 + i * 2048, 16, 512) ^ (3ull << 62); \
            wgmma_n32<0>(d + i * 16, da, db); wgmma_n32<1>(d + i * 16, da + 2, db + 64); \
          } \
          wgmma_commit(); \
          PUMP0(); \
          ACC_FENCE(d, 32); \
          bar_wg(wg); \
          _Pragma("unroll") for (int i = 0; i < 4; i++) { \
            const float* x = d + (i & 1) * 8 + (i >> 1) * 2; \
            if (rd) sts128((tile) + wg * 8192 + ((warp & 3) * 16 + (i >> 1) * 8 + g) * 128 + (((2 * t + (i & 1)) ^ g) << 4), \
                           pack_bf16(x[0], x[1]), pack_bf16(x[4], x[5]), pack_bf16(x[16], x[17]), pack_bf16(x[20], x[21])); \
            else stsm_x4((tile) + srowoff + ((((uint32_t)i << 5) + lhi) ^ lsw), pack_bf16(d[i * 8], d[i * 8 + 1]), pack_bf16(d[i * 8 + 2], d[i * 8 + 3]), \
                         pack_bf16(d[i * 8 + 4], d[i * 8 + 5]), pack_bf16(d[i * 8 + 6], d[i * 8 + 7])); \
          } \
          }
#define LOAD_X0(base) \
      _Pragma("unroll") for (int j = 0; j < 8; j++) { \
        uint32_t x0, x1, x2, x3; \
        ldsm_x4((base) + (j >> 2) * SLOT + srowoff + ((((uint32_t)(j & 3) << 5) + lhi) ^ lsw), x0, x1, x2, x3); \
        S1[j * 8 + 0] = bf_lo(x0); S1[j * 8 + 1] = bf_hi(x0); S1[j * 8 + 2] = bf_lo(x1); S1[j * 8 + 3] = bf_hi(x1); \
        S1[j * 8 + 4] = bf_lo(x2); S1[j * 8 + 5] = bf_hi(x2); S1[j * 8 + 6] = bf_lo(x3); S1[j * 8 + 7] = bf_hi(x3); \
      }
#define XM_ISSUE(keep) { mbar_wait(bar_xr, par); wgmma_fence(); \
      wgmma_copy(T_, dA0 + (OFF_RA >> 4), ((keep) ? make_desc(sbase + OFF_ID + 128, 0, 0) : make_desc(sbase + OFF_ID, 128, 128)) ^ (1ull << 62), keep); }
#define COPYN(d, s, n) _Pragma("unroll") for (int i_ = 0; i_ < (n); i_++) { uint32_t c_; asm volatile("mov.b32 %0, %1;" : "=r"(c_) : "f"((s)[i_])); (d)[i_] = __uint_as_float(c_); }
#define COPY64(d, s) COPYN(d, s, 64)
#define XM_DONE(c) { ACC_FENCE(T_, 64); COPY64(S1, T_); ACC_FENCE(S1, 64); \
      __syncwarp(); if ((c) && elect_one()) mbar_arrive_local(bar_lx); }
#define LOAD_X() { float T_[64]; ACC_DEF(T_, 64); wgmma_wait<0>(); XM_ISSUE(0); wgmma_commit(); wgmma_wait<0>(); XM_DONE(true); }

    float S0[96], S1[96];
#define FIRST_STEP(l_) { const int ln_ = (l_), l = ln_; const uint32_t par = l & 1, ub = bar_full; ACC_DEF(S0, 96); QSTEP(S0, dA0 + (OFF_S >> 4), 0, {}); }
    FIRST_STEP(0);
    LOAD_EPOCH();
#pragma unroll 1
    for (int l = 0;; l++) {
      const uint32_t par = l & 1;
      uint32_t ub = bar_full + 8;
      PROF(1);
      {
        LANE_CONSTS();
        uint32_t ta[4];
#pragma unroll
        for (int j = 0; j < 4; j++) ta[j] = pK + srowoff + ((((uint32_t)j << 5) + lhi) ^ lsw);
        float p0, p1, a0 = 0.f, a1 = 0.f, q0 = 0.f, q1 = 0.f;
#define STATS(j0, j1) _Pragma("unroll") for (int j = (j0); j < (j1); j++) { \
          uint32_t x[4]; \
          ldsm_x4(ta[j & 3] + (j >> 2) * SLOT, x[0], x[1], x[2], x[3]); \
          if (j == 0) { p0 = __shfl_sync(0xffffffffu, bf_lo(x[0]), lane & 28); p1 = __shfl_sync(0xffffffffu, bf_lo(x[1]), lane & 28); } \
          _Pragma("unroll") for (int i = 0; i < 4; i += 2) { \
            const float d0 = bf_lo(x[i]) - p0, d1 = bf_hi(x[i]) - p0, d2 = bf_lo(x[i + 1]) - p1, d3 = bf_hi(x[i + 1]) - p1; \
            a0 += d0 + d1; a1 += d2 + d3; \
            q0 = fmaf(d1, d1, fmaf(d0, d0, q0)); q1 = fmaf(d3, d3, fmaf(d2, d2, q1)); } } \
          asm volatile("" : "+f"(a0), "+f"(a1), "+f"(q0), "+f"(q1), "+f"(p0), "+f"(p1)); SCHED_FENCE()
        if (SB0) { STATS(0, SB0); }
        if (!(NOBW >> 0 & 1)) bar_wg(wg);
        QSTEP(S0, dA0 + ((OFF_S + SLOT) >> 4), 1, {});
        QREL();
        SCHED_FENCE();
        STATS(SB0, SB1);
        ACC_DEF(S1, 96);
        QSTEP(S1, dA0 + (OFF_S >> 4), 0, {});
        QREL();
        SCHED_FENCE();
        STATS(SB1, SB2);
        QSTEP(S1, dA0 + ((OFF_S + SLOT) >> 4), 1, {});
        QREL();
        SCHED_FENCE();
        STATS(SB2, 8);
#pragma unroll
        for (int o = 1; o <= 2; o <<= 1) {
          a0 += __shfl_xor_sync(0xffffffffu, a0, o); a1 += __shfl_xor_sync(0xffffffffu, a1, o);
          q0 += __shfl_xor_sync(0xffffffffu, q0, o); q1 += __shfl_xor_sync(0xffffffffu, q1, o);
        }
        if (t == 1) { a0 = a1; q0 = q1; p0 = p1; }
        if (t < 2) st_b64(g_stats + (size_t)(mm * 128 + r0 + g + t * 8) * 8 + jj, __float_as_uint(fmaf(a0, 1.f / 128.f, p0)),
                          (__float_as_uint(fmaxf(fmaf(a0 * (-1.f / 128.f), a0, q0), 0.f)) & ~3u) | STAT_TAG(l));
        if (l) { asm volatile("cp.async.bulk.wait_group 0;" ::: "memory"); bar_arrive<BAR_X1, 288>(); }
#pragma unroll 1
        for (int i = 0; i < 14; i++) {
          QSTEP(S0, RA_CUR, 1, {});
          if (i == 0) PROF(2);
          QREL();
        }
      }
      LANE_CONSTS();
      mbar_wait(bar_stat, par);
      LNSTEP(S0, 0);
      wgmma_commit();
      const float rs0 = lds32f(sbase + OFF_ST + (r0 + g) * 4), rs1 = lds32f(sbase + OFF_ST + (r0 + g + 8) * 4);
      PUMP0();
      ACC_FENCE(S0, 96);
      PROF(3);
      if (!par) {
        constexpr uint32_t par = 0;
        uint32_t qa[16];
        uint32_t kf[32], vf[32];
#define DRAIN_A(ACC, hp, PMP) { \
          LANE_CONSTS(); \
          FRAG(kf + 16, ACC + 32, 0, (hp) * 2); \
          PMP; \
          FRAG(vf + 16, ACC + 64, 1, (hp) * 2 + 1); \
          _Pragma("unroll") for (int i_ = 0; i_ < 16; i_++) qa[i_] = pack_bf16(ACC[2 * i_], ACC[2 * i_ + 1]); \
          PINU(qa, 16); }
        DRAIN_A(S0, 0, PUMP0());
        if (l == 0 && NLAYERS > 1) {
#pragma unroll 1
          for (int rd = 1; rd >= 0; rd--) {
            FOLD(sbase + (12 - rd) * SLOT, rd);
            fence_proxy_async_smem();
            asm volatile("bar.arrive %0, 288;" :: "r"(BAR_WF + 1 - rd) : "memory");
          }
        }
        PUMPS(FPUMP);
        if (l == 0 && NLAYERS > 1) mbar_wait(bar_phi, 1);
#pragma unroll 1
        for (int h = 0; h < 2; h++) {
          const uint32_t pO = sbase + (h ? 3 : 12) * SLOT;
          PROFH(4, 16);
          LANE_CONSTS();
          if (XA && h) {
            float T_[64];
            ACC_DEF(T_, 64);
            if (XA == 2) { FRAG_PUT(kf + 16, 10); }
            XM_ISSUE(0); wgmma_commit();
            SCHED_FENCE();
            if (XA == 1) { FRAG_PUT(kf + 16, 10); }
            FRAG_PUT(vf + 16, 11);
            STG_ARRIVE();
            SCHED_FENCE();
            wgmma_wait<0>(); XM_DONE(true);
          } else {
            FRAG_PUT(kf + 16, 10); FRAG_PUT(vf + 16, 11);
            STG_ARRIVE();
          }
          if (h) { if (!XA && AW0 < 4) LOAD_X(); if (AW0 == 1) WSTEP(); } else PUMPS(HPUMP2);
          const bool e = g & 1, hb = (2 * t + (g & 1)) <= g;
          uint32_t sel[3] = {e ? 0x1044u : 0x4410u, hb ? 0x4444u : (e ? 0x3244u : 0x4432u), hb ? (e ? 0x3244u : 0x4432u) : 0x4444u};
          PINU(sel, 3);
          TILE_CONSTS(pO, true, O_BIT(l));
          const uint32_t selA = sel[0], selL = sel[1], selH = sel[2];
          STG_WAIT();
          if (warp == 0) mbar_wait(bar_halo, h);
          FRAG_GET(kf, 10);
          PROFH(5, 17);
          float s[2][4][4];
#pragma unroll
          for (int ks = 0; ks < 2; ks++)
#pragma unroll
            for (int i = 0; i < 8; i++) {
              const int hh = (i >> 1) & 1, jb = (i & 1) + (~i >> 1 & 2);
              const uint32_t* b = kf + (jb >> 1) * 16 + hh * 8 + ks * 4 + (jb & 1) * 2;
              if (ks) mma_bf16(s[hh][jb], qa[hh * 8 + 4], qa[hh * 8 + 5], qa[hh * 8 + 6], qa[hh * 8 + 7], b[0], b[1]);
              else mma_bf16_z(s[hh][jb], qa[hh * 8], qa[hh * 8 + 1], qa[hh * 8 + 2], qa[hh * 8 + 3], b[0], b[1]);
            }
          if (h == 0) PUMP1() else if (AW0 == 2 || AW0 == 4) { if (AW0 == 4) LOAD_X(); WSTEP(); }
          PROFH(6, 18);
          float va[2][2], vb[2][2], mx[2][2];
#pragma unroll
          for (int hh = 0; hh < 2; hh++) {
            va[hh][0] = e ? s[hh][1][1] : s[hh][1][0];
            vb[hh][0] = hb ? (e ? s[hh][2][1] : s[hh][2][0]) : (e ? s[hh][0][1] : s[hh][0][0]);
            va[hh][1] = e ? s[hh][2][3] : s[hh][2][2];
            vb[hh][1] = hb ? (e ? s[hh][3][3] : s[hh][3][2]) : (e ? s[hh][1][3] : s[hh][1][2]);
          }
          if (warp == 0 && mm == 0) {
#pragma unroll
            for (int hh = 0; hh < 2; hh++) { va[hh][0] = -INFINITY; if (!hb) { vb[hh][0] = -INFINITY; vb[hh][1] = -INFINITY; } }
          }
#pragma unroll
          for (int i = 0; i < 4; i++) mx[i >> 1][i & 1] = fmaxf(va[i >> 1][i & 1], vb[i >> 1][i & 1]);
#pragma unroll
          for (int o = 1; o <= 2; o <<= 1)
#pragma unroll
            for (int i = 0; i < 4; i++) mx[i >> 1][i & 1] = fmaxf(mx[i >> 1][i & 1], __shfl_xor_sync(0xffffffffu, mx[i >> 1][i & 1], o));
          const float sc0 = rs0 * (0.17677669529663687f * LOG2E), sc1 = rs1 * (0.17677669529663687f * LOG2E);
#pragma unroll
          for (int i = 0; i < 4; i++) {
            const float sc = (i & 1) ? sc1 : sc0, m = mx[i >> 1][i & 1];
            va[i >> 1][i & 1] = ex2((va[i >> 1][i & 1] - m) * sc); vb[i >> 1][i & 1] = ex2((vb[i >> 1][i & 1] - m) * sc);
            mx[i >> 1][i & 1] = va[i >> 1][i & 1] + vb[i >> 1][i & 1];
          }
          if (h == 0 && ASITE) { PIN(&va[0][0], 4); PIN(&vb[0][0], 4); PIN(&mx[0][0], 4); PUMP1(); } else if (AW0 == 3) WSTEP();
          if (warp == 0) mbar_wait(bar_halo + 8, h);
          FRAG_GET(vf, 11);
#pragma unroll
          for (int o = 1; o <= 2; o <<= 1)
#pragma unroll
            for (int i = 0; i < 4; i++) mx[i >> 1][i & 1] += __shfl_xor_sync(0xffffffffu, mx[i >> 1][i & 1], o);
          float o[2][4][4];
          uint32_t pa[2][8];
#pragma unroll
          for (int hh = 0; hh < 2; hh++) {
            const float i0 = rcp_fast(mx[hh][0]), i1 = rcp_fast(mx[hh][1]);
            const uint32_t w0 = pack_bf16(va[hh][0] * i0, vb[hh][0] * i0), w1 = pack_bf16(va[hh][1] * i1, vb[hh][1] * i1);
            pa[hh][0] = __byte_perm(w0, 0, selL); pa[hh][2] = __byte_perm(w0, 0, selA); pa[hh][3] = __byte_perm(w1, 0, selL);
            pa[hh][4] = __byte_perm(w0, 0, selH); pa[hh][5] = __byte_perm(w1, 0, selA); pa[hh][7] = __byte_perm(w1, 0, selH);
            pa[hh][1] = pa[hh][0] & pa[hh][4]; pa[hh][6] = pa[hh][3] & pa[hh][7];
          }
          PROFH(7, 19);
#pragma unroll
          for (int i = 0; i < 8; i++) mma_bf16_z(o[i >> 2][i & 3], pa[i >> 2][4], pa[i >> 2][5], pa[i >> 2][6], pa[i >> 2][7], vf[16 + 2 * i], vf[17 + 2 * i]);
#pragma unroll
          for (int i = 0; i < 8; i++) mma_bf16(o[i >> 2][i & 3], pa[i >> 2][0], pa[i >> 2][1], pa[i >> 2][2], pa[i >> 2][3], vf[2 * i], vf[2 * i + 1]);
          if (h == 0) PUMP1() else mbar_wait(bar_done + 30 * 8, par);
          if (NLAYERS > 1) mbar_wait(bar_phi + 8, 0);
#pragma unroll
          for (int i = 0; i < 4; i++) {
            const int hh = i >> 1, dp = i & 1;
            stsm_x4(ta[i],
                    PBIT0(pack_bf16(o[hh][dp * 2][0], o[hh][dp * 2][1])), PBIT0(pack_bf16(o[hh][dp * 2][2], o[hh][dp * 2][3])),
                    PBIT1(pack_bf16(o[hh][dp * 2 + 1][0], o[hh][dp * 2 + 1][1])), PBIT1(pack_bf16(o[hh][dp * 2 + 1][2], o[hh][dp * 2 + 1][3])));
          }
          PUBLISH_O();
          PROFH(11, 23);
          if (h) break;
          REST_P1(ASKEW);
          asm volatile("cp.async.bulk.wait_group.read 0;" ::: "memory");
          DRAIN_A(S1, 1, {});
        }
      } else {
        constexpr uint32_t par = 1;
        float st[32];
        const float c0 = rs0 * LOG2E, c1 = rs1 * LOG2E;
        { V_ADDR(pV); STAGE_V(S0 + 64); }
        if (warp < 2) sts128(sbase + OFF_ONES + warp * 512 + lane * 16, 0x3F803F80u, 0x3F803F80u, 0x3F803F80u, 0x3F803F80u);
        scale32(st, S0, c0, c1);
        PIN(st, 32);
#define KV_MMA(vs) { \
          const uint32_t dp = dA0 + 12 * 1024 - wg * 2560, dv = dA0 + (vs) * 1024 + ((OFF_ONES - (vs) * SLOT - 16) << 12) - wg * (512 << 16); \
          STG_WAIT(); \
          wgmma_fence(); \
          _Pragma("unroll") for (int ks = 0; ks < 8; ks++) { \
            const uint64_t a = DESC(dp + ks * 128, 0x40000040), b = DESC(dv + ks * (64 - (64 << 16)), 0x80000020); \
            if (ks == 0) wgmma_n40<0, 1>(kv, a, b); else wgmma_n40<1, 1>(kv, a, b); } \
          wgmma_commit(); }
#define KV_RED(hp) { \
          float* kvg = g_kv[l >> 1] + (jj * 4 + (hp) * 2) * KVH + warp * 768 + lane * 4; \
          _Pragma("unroll") for (int i = 0; i < 5; i++) red_v4(kvg + i * 128, kv[i * 3], kv[i * 3 + 1], kv[i * 3 + 2], 1.f); \
          red_v4(kvg + 640, kv[15], kv[16], kv[18], 1.f); }
#define KV_RED1(i) if (h) red_v4(g_kv[l >> 1] + (jj * 4) * KVH + warp * 768 + lane * 4 + (i) * 128, S0[32 + (i) * 3], S0[33 + (i) * 3], S0[34 + (i) * 3], 1.f)
#define KV_REDS(n) { if (PAIR & 1) { if (h && (n) == PPOS0) KV_RECV(S0 + 32, 0); } else _Pragma("unroll") for (int i_ = 0; i_ < 6; i_++) if (((RPACE >> (4 * i_)) & 15) == (n)) KV_RED1(i_); }
#define KV_SEND(kp) { \
          float sd[9]; \
          kv[17] = kv[18]; \
          _Pragma("unroll") for (int i = 0; i < 9; i++) { (kp)[i] = rank ? kv[9 + i] : kv[i]; sd[i] = rank ? kv[i] : kv[9 + i]; } \
          const uint32_t ra = sbase + peer + (warp * 32 + lane) * 4, rb = bar_kx + peer; \
          if (elect_one()) mbar_expect_tx(bar_kx, 1152); \
          _Pragma("unroll") for (int i = 0; i < 2; i++) \
            asm volatile("st.async.weak.shared::cluster.mbarrier::complete_tx::bytes.v4.f32 [%0], {%1, %2, %3, %4}, [%5];" \
                         :: "r"(ra + (warp * 32 + lane) * 12 + OFF_PHI + i * 4096), "f"(sd[4 * i]), "f"(sd[4 * i + 1]), "f"(sd[4 * i + 2]), "f"(sd[4 * i + 3]), "r"(rb) : "memory"); \
          asm volatile("st.async.weak.shared::cluster.mbarrier::complete_tx::bytes.f32 [%0], %1, [%2];" :: "r"(ra + OFF_LNB), "f"(sd[8]), "r"(rb) : "memory"); }
#define KV_RECV(kp, hp) { \
          float r_[9]; \
          float* kvg = g_kv[l >> 1] + (jj * 4 + (hp) * 2) * KVH + warp * 768 + rank * 384 + lane * 4; \
          mbar_wait(bar_kx, PAIR == 3 ? (hp) : (l >> 1)); \
          _Pragma("unroll") for (int i = 0; i < 2; i++) \
            asm volatile("ld.shared.v4.f32 {%0, %1, %2, %3}, [%4];" : "=f"(r_[4 * i]), "=f"(r_[4 * i + 1]), "=f"(r_[4 * i + 2]), "=f"(r_[4 * i + 3]) \
                         : "r"(sbase + OFF_PHI + i * 4096 + (warp * 32 + lane) * 16) : "memory"); \
          r_[8] = lds32f(sbase + OFF_LNB + (warp * 32 + lane) * 4); \
          _Pragma("unroll") for (int i = 0; i < 3; i++) red_v4(kvg + i * 128, (kp)[3 * i] + r_[3 * i], (kp)[3 * i + 1] + r_[3 * i + 1], (kp)[3 * i + 2] + r_[3 * i + 2], 2.f); }
#define KV_LOAD(hp) { \
          const uint4* kvg = reinterpret_cast<const uint4*>(g_kv[l >> 1] + (jj * 4 + (hp) * 2) * KVH) + warp * 192 + lane; \
          _Pragma("unroll") for (int i = 0; i < 6; i++) v[i] = ld_b128(kvg + i * 32); }
#define KVV(i) __uint_as_float((i) % 3 == 0 ? v[(i) / 3].x : ((i) % 3 == 1 ? v[(i) / 3].y : v[(i) / 3].z))
#define KV_TILE(hp) { \
          _Pragma("unroll 1") for (int it = 0; it < (1 << 16); it++) { \
            if (__all_sync(0xffffffffu, (v[0].w & v[1].w & v[2].w & v[3].w & v[4].w & v[5].w) == 0x41800000u)) break; \
            RETRY_COUNT(); \
            KV_LOAD(hp); \
          } \
          if (hp) PROF(26); else PROF(25); \
          const uint32_t e = lane & 7, jt = ((lane >> 1) & 4) + (e >> 1); \
          const uint32_t row = ((((warp >> 1) ^ wg) & 1) << 5) + ((jt & 1) << 4) + ((warp & 1) << 3) + (jt & 6) + (e & 1); \
          const uint32_t kd = pV + wg * 8192 + row * 128, ksw = (row & 7) << 4; \
          _Pragma("unroll") for (int i = 0; i < 2; i++) \
            stsm_x4(kd + ((i * 32 + lhi) ^ ksw), pack_bf16(KVV(i * 8), KVV(i * 8 + 1)), pack_bf16(KVV(i * 8 + 2), KVV(i * 8 + 3)), \
                    pack_bf16(KVV(i * 8 + 4), KVV(i * 8 + 5)), pack_bf16(KVV(i * 8 + 6), KVV(i * 8 + 7))); \
          stsm_x4(kd + ((64u + lhi) ^ ksw), pack_bf16(KVV(16), 1.f), pack_bf16(KVV(17), 1.f), 0u, 0u); }
#pragma unroll 1
        for (int h = 0; h < 2; h++) {
          PROFH(4, 6);
          SITE(0);
          LANE_CONSTS();
          const uint32_t dsw = (uint32_t)(g ^ (2 * t)) << 4, dst = ((t & 2) ? pK : sbase + 12 * SLOT) + (r0 + g) * 128;
          float e[16], f[16];
          KV_REDS(1);
          float sa = exps16_<0>(e, st);
          exps16_fix<0>(e, st, sa);
          asm volatile("" : "+f"(sa)); PIN(e, 16); SITE(1);
          if (h) STG_WAIT();
          KV_REDS(2);
          store16(e, sa, dst, dsw, 4);
          float sb = exps16_<1>(f, st);
          exps16_fix<1>(f, st, sb);
          asm volatile("" : "+f"(sb)); PIN(f, 16); SITE(2);
          KV_REDS(3);
          store16(f, sb, dst, dsw, 0);
          float sc = exps16_<0>(e, st + 2);
          exps16_fix<0>(e, st + 2, sc);
          asm volatile("" : "+f"(sc)); PIN(e, 16); SITE(3);
          KV_REDS(4);
          store16(e, sc, dst + 1024, dsw, 4);
          float sd = exps16_<1>(f, st + 2);
          exps16_fix<1>(f, st + 2, sd);
          asm volatile("" : "+f"(sd)); PIN(f, 16); SITE(4);
          store16(f, sd, dst + 1024, dsw, 0);
          PROFH(5, 7);
          if (h) break;
          {
            float kv[20];
            ACC_DEF(kv, 20);
            fence_proxy_async_smem();
            STG_ARRIVE();
            KV_MMA(11);
            PUMP0();
            ACC_FENCE(kv, 20);
            STG_ARRIVE();
            scale32(st, S0 + 32, c0, c1);
            PIN(st, 32);
            if (PAIR & 1) { KV_SEND(S0 + 32); PIN(S0 + 32, 9); }
            else {
              kv[17] = kv[18];
              COPYN(S0 + 32, kv, 18);
              const int h = 1;
              KV_REDS(0);
            }
          }
        }
        bool big;
        uint4 v[6];
        {
          float kv[20];
          if (KT0) { LANE_CONSTS(); KV_LOAD(0); }
          mbar_wait(bar_stat2, par);
          LNSTEP(S1, 1);
          ub = bar_full + 240;
          PUMP1();
          if (wg == 0) bar_sync<BAR_SKEW, 256>();
          QSTEP(S1, RA_CUR, 1, {});
          if (wg == 1) bar_arrive<BAR_SKEW, 256>();
          QREL();
          if (KT0 == 2) { LANE_CONSTS(); KV_TILE(0); }
          LANE_CONSTS();
          V_ADDR(sbase + 3 * SLOT);
          PINU(va_, 2);
          mbar_wait(bar_done + 30 * 8, par);
          wgmma_wait<0>();
          ACC_FENCE(S1, 96);
          if (!(RLATE & 2)) REL(bar_done + 31 * 8);
          PROF(13);
          STAGE_V(S1 + 64);
          fence_proxy_async_smem();
          STG_ARRIVE();
          if (RLATE & 2) REL(bar_done + 31 * 8);
          scale32(st, S1, c0, c1);
          PIN(st, 32);
          PROF(16);
          ACC_DEF(kv, 20);
          KV_MMA(3);
          SCHED_FENCE();
          if (!KT0) KV_LOAD(0);
          big = any_big(st);
          if (EROT > 0) { phiq_a(st, big); PIN(st, 16); }
          SCHED_FENCE();
          wgmma_wait<0>();
          ACC_FENCE(kv, 20);
          if (PAIR & 2) { float kp[9]; KV_SEND(kp); _Pragma("unroll") for (int i = 0; i < 3; i++) v[i] = make_uint4(__float_as_uint(kp[3 * i]), __float_as_uint(kp[3 * i + 1]), __float_as_uint(kp[3 * i + 2]), 0u); }
          else KV_RED(1);
          PROF(17);
        }
#pragma unroll 1
        for (int h = 0; h < 2; h++) {
          const uint32_t pO = sbase + (h ? 3 : 8) * SLOT;
          LANE_CONSTS();
          uint32_t fq[32];
#define KV_RECV1(pos) if ((PAIR & 2) && PPOS == (pos) && h == 0) { float kp[9]; _Pragma("unroll") for (int i = 0; i < 9; i++) kp[i] = KVV(i); KV_RECV(kp, 1); SCHED_FENCE(); }
          KV_RECV1(0);
          PROFH(18, 32);
          SCHED_FENCE();
          if (h) {
            asm volatile("cp.async.bulk.wait_group.read 0;" ::: "memory");
            mbar_wait(bar_lx, par);
          }
          if (h || KT0 < 2) {
            KV_TILE(h);
            fence_proxy_async_smem();
            STG_ARRIVE();
          }
          SCHED_FENCE();
          phiq_b<1>(fq, st, big); PINU(fq, 16); PIN(st + 16, 16);
          KV_RECV1(1);
          if (h || KT0 < 2) STG_WAIT();
          wgmma_wait<0>();
          ACC_FENCE(S1, 64);
          float T_[64];
          if (XB == 3) { COPY64(T_, S1); }
          PROFH(19, 33);
          float o[4][20];
#define O_MMA(hh) { \
            const uint64_t db = make_desc(pV + (hh) * 8192, 16, 1024); \
            ACC_DEF(o[(hh) * 2], 20); ACC_DEF(o[(hh) * 2 + 1], 20); \
            wgmma_fence(); \
            wgmma_n40_rs<0>(o[(hh) * 2], fq + (hh) * 16, db + 256); wgmma_n40_rs<0>(o[(hh) * 2 + 1], fq + (hh) * 16 + 8, db); \
            wgmma_n40_rs<1>(o[(hh) * 2], fq + (hh) * 16 + 4, db + 384); wgmma_n40_rs<1>(o[(hh) * 2 + 1], fq + (hh) * 16 + 12, db + 128); \
            wgmma_commit(); }
          O_MMA(0);
          SCHED_FENCE();
          KV_RECV1(2);
          phiq_b<0>(fq + 16, st + 16, big); PINU(fq + 16, 16);
          KV_RECV1(3);
          SCHED_FENCE();
          PMASKS(true, O_BIT(l));
#pragma unroll
          for (int hh = 0; hh < 2; hh++) {
            if (hh && !OW) O_MMA(1);
            if (XB == 3 && hh) { scale32(st, T_ + 32, c0, c1); PIN(st, 32); XM_ISSUE(h); wgmma_commit(); wgmma_wait<1>(); } else
            wgmma_wait<0>();
            ACC_FENCE(o[hh * 2], 20); ACC_FENCE(o[hh * 2 + 1], 20);
            if (!hh && OW) { O_MMA(1); SCHED_FENCE(); }
            const float* x = o[hh * 2];
            const float* y = o[hh * 2 + 1];
            const float sx0 = x[17] * 0x1p-40f, sy0 = y[17] * 0x1p-40f, sx1 = x[19] * 0x1p-40f, sy1 = y[19] * 0x1p-40f;
            const float i0 = rcp_fast(fmaf(fmaf(x[17], 1e-6f, x[16]), sy0, y[16] * sx0)), i1 = rcp_fast(fmaf(fmaf(x[19], 1e-6f, x[18]), sy1, y[18] * sx1));
            const float ax0 = sy0 * i0, ay0 = sx0 * i0, ax1 = sy1 * i1, ay1 = sx1 * i1;
#pragma unroll
            for (int dp = 0; dp < 2; dp++)
              stsm_x4(pO + srowoff + ((hh * 64 + dp * 32 + lhi) ^ lsw),
                      PBIT0(pack_bf16(fmaf(x[dp * 8], ax0, y[dp * 8] * ay0), fmaf(x[dp * 8 + 1], ax0, y[dp * 8 + 1] * ay0))),
                      PBIT0(pack_bf16(fmaf(x[dp * 8 + 2], ax1, y[dp * 8 + 2] * ay1), fmaf(x[dp * 8 + 3], ax1, y[dp * 8 + 3] * ay1))),
                      PBIT1(pack_bf16(fmaf(x[dp * 8 + 4], ax0, y[dp * 8 + 4] * ay0), fmaf(x[dp * 8 + 5], ax0, y[dp * 8 + 5] * ay0))),
                      PBIT1(pack_bf16(fmaf(x[dp * 8 + 6], ax1, y[dp * 8 + 6] * ay1), fmaf(x[dp * 8 + 7], ax1, y[dp * 8 + 7] * ay1))));
          }
          PUBLISH_O();
          if (XB == 3) { wgmma_wait<0>(); XM_DONE(h == 0); }
          PROFH(20, 34);
          if (h) break;
          if (KVL == 2) { KV_LOAD(1); SCHED_FENCE(); }
          if (!XB) {
            scale32(st, S1 + 32, c0, c1);
            PIN(st, 32);
            LOAD_X();
          }
          if (XB == 4) {
            scale32(st, S1 + 32, c0, c1);
            PIN(st, 32);
            ACC_DEF(T_, 64);
            XM_ISSUE(0); wgmma_commit();
            SCHED_FENCE();
            KV_LOAD(1);
            big = any_big(st);
            SCHED_FENCE();
            wgmma_wait<0>(); XM_DONE(true);
          }
          if (!(NOBW >> 2 & 1)) bar_wg(wg);
          WSTEP();
          SCHED_FENCE();
          if (KVL == 0 && XB != 4) KV_LOAD(1);
          if (XB != 4) big = any_big(st);
          if (KVL == 1) { SCHED_FENCE(); KV_LOAD(1); }
          if (EROT > 0) { phiq_a(st, big); PIN(st, 16); }
          PROF(31);
        }
      }
      __syncwarp();
      if (elect_one()) mbar_arrive_local(bar_epi);
      if (!(NOBW >> 3 & 1)) bar_wg(wg);
#pragma unroll 1
      while (ub < bar_full + 384) {
        WSTEP();
        if (ub == bar_full + 8 * 41) { asm volatile("cp.async.bulk.wait_group.read 0;" ::: "memory"); PROF(35); }
        if (ub == bar_full + 8 * 42) PROF(36);
      }
      {
        float Wb[32];
        LANE_CONSTS();
        TILE_CONSTS(pK, l < NLAYERS - 1, X_BIT(l));
        wgmma_wait<0>();
        ACC_FENCE(S1, 64);
        COPYN(Wb, S1 + 32, 32);
        PROF(37);
        X_OUT(0, S1);
        WARP_STORE(l < NLAYERS - 1 ? &tm_os : &tm_xo, pK, jj * 128, mm * 128 + (l < NLAYERS - 1 ? S_LEN : 0));
        if (l == NLAYERS - 1) { PMASKS(false, 0); X_OUT(1, Wb); break; }
        REL(bar_done + 47 * 8);
        PROF(38);
        if (!(NOBW >> 4 & 1)) bar_wg(wg);
        FIRST_STEP(l + 1);
        PROF(39);
        { PMASKS(false, 0); X_OUT(1, Wb); }
        fence_proxy_async_smem();
      }
    }
    WARP_STORE(&tm_xo, pV, jj * 128 + 64, mm * 128);
    asm volatile("cp.async.bulk.wait_group.read 0;" ::: "memory");
    cluster_sync();
  }
}

typedef CUresult (*PFN_encode)(CUtensorMap*, CUtensorMapDataType, cuuint32_t, void*, const cuuint64_t*, const cuuint64_t*,
                               const cuuint32_t*, const cuuint32_t*, CUtensorMapInterleave, CUtensorMapSwizzle,
                               CUtensorMapL2promotion, CUtensorMapFloatOOBfill);

CUtensorMap make_map(PFN_encode enc, const void* ptr, uint64_t inner, uint64_t outer, uint32_t box_inner, uint32_t box_outer,
                     CUtensorMapSwizzle swz = CU_TENSOR_MAP_SWIZZLE_128B, int promo = CU_TENSOR_MAP_L2_PROMOTION_L2_256B) {
  CUtensorMap m;
  cuuint64_t dims[2] = {inner, outer};
  cuuint64_t strides[1] = {inner * 2};
  cuuint32_t box[2] = {box_inner, box_outer};
  cuuint32_t es[2] = {1, 1};
  enc(&m, CU_TENSOR_MAP_DATA_TYPE_BFLOAT16, 2, const_cast<void*>(ptr), dims, strides, box, es, CU_TENSOR_MAP_INTERLEAVE_NONE,
      swz, (CUtensorMapL2promotion)promo, CU_TENSOR_MAP_FLOAT_OOB_FILL_NONE);
  return m;
}

}

extern "C" void kernel_launch(void* const* d_in, const int* in_sizes, int n_in, void* d_out, int out_size) {
  (void)in_sizes; (void)n_in; (void)out_size;
  static PFN_encode enc = nullptr;
  if (!enc) {
    void* fn = nullptr;
    cudaDriverEntryPointQueryResult qr;
    cudaGetDriverEntryPoint("cuTensorMapEncodeTiled", &fn, cudaEnableDefault, &qr);
    enc = (PFN_encode)fn;
    cudaFuncSetAttribute(mega_kernel, cudaFuncAttributeMaxDynamicSharedMemorySize, SMEM_BYTES);
  }
  Params prm;
  prm.x0 = (const __nv_bfloat16*)d_in[0];
  prm.wA_qkv = (const __nv_bfloat16*)d_in[1];
  prm.wA_o = (const __nv_bfloat16*)d_in[2];
  prm.wB_qkv = (const __nv_bfloat16*)d_in[4];
  prm.wB_phi = (const __nv_bfloat16*)d_in[5];
  prm.wB_o = (const __nv_bfloat16*)d_in[6];
  prm.out = (__nv_bfloat16*)d_out;
  void *obuf = nullptr, *wf = nullptr;
  cudaGetSymbolAddress(&obuf, g_obuf);
  cudaGetSymbolAddress(&wf, g_wfold);
  CUtensorMap tm_x0 = make_map(enc, d_in[0], D_MODEL, S_LEN, 64, 128, CU_TENSOR_MAP_SWIZZLE_128B, XPROMO);
  CUtensorMap tm_xo = make_map(enc, d_out, D_MODEL, S_LEN, 64, 16);
  CUtensorMap tm_os = make_map(enc, obuf, D_MODEL, 2 * S_LEN, 64, 16);
  CUtensorMap tm_o = make_map(enc, obuf, D_MODEL, 2 * S_LEN, 64, 128, CU_TENSOR_MAP_SWIZZLE_128B, OPROMO);
  CUtensorMap tm_wf = make_map(enc, wf, 2048, D_MODEL, 64, 32);
  CUtensorMap tm_wqA = make_map(enc, d_in[1], 3 * D_MODEL, D_MODEL, 64, 32, CU_TENSOR_MAP_SWIZZLE_128B, WPROMO);
  CUtensorMap tm_wqB = make_map(enc, prm.wB_qkv, 3 * D_MODEL, D_MODEL, 64, 32);
  CUtensorMap tm_woA = make_map(enc, prm.wA_o, D_MODEL, D_MODEL, 64, 64);
  CUtensorMap tm_woB = make_map(enc, prm.wB_o, D_MODEL, D_MODEL, 64, 64);
  CUtensorMap tm_phi = make_map(enc, prm.wB_phi, 32, 1024, 32, 128, CU_TENSOR_MAP_SWIZZLE_64B);
  mega_kernel<<<NMAIN + NAUX, 384, SMEM_BYTES>>>(tm_x0, tm_xo, tm_os, tm_o, tm_wf, tm_wqA, tm_wqB, tm_woA, tm_woB, tm_phi, prm);
}
```

```cpp
#include <cuda_runtime.h>
#include <cuda.h>
#include <cuda_bf16.h>
#include <stdint.h>

#define NLAYERS 4

#define STAG1 0
#define HPUMP1 2
#define HPUMP2 1
#define ASKEW 2
#define FPUMP 3
#define PFGAP 100
#define POLLGAP 120
#define OW 1
#define AW0 1
#define RLATE 3
#define FSTART 0
#define MAPV 1
#define HW1 29
#define XPACE 0x06050401000000ull
#define XP0 4
#define HW0 18
#define XD 4
#define WFGAP 50
#define KT0 2
#define W23 0
#define AX 0
#define PF0 1
#define ORD 0
#define EARLY (2 + ORD)
#define UPS(u) (ORD ? (u) & 1 : (u) >> 1)
#define USL(u) (ORD ? (u) >> 1 : (u) & 1)
#define BIGLIM 3600.f
#define SUMLO 0x1p-100f
#define SUMHI 0x1p100f
#define EROT 1
#define FINW 0
#define AHOIST 1
#define EMRG 1
#define XPROMO 2
#define OPROMO 3
#define STAG2 300
#define WPROMO 3
#define SB0 2
#define SB1 4
#define SB2 6
#define KVL 0
#define BMASK 0x1F
#define ASITE 1
#define NEWOPTS
#define PROWS 3
#define HSL 0
#define HDEL 0
#define HDEL1 0
#define SPD0 0
#define SPD1 0
#define SPD2 300
#define FRB 0x3535353535ull
#define NOB 0xFFFFFF00u
#define NO1 ~0u
#define NOX ~0u
#define ILV 1
#define SEARLY 0
#define PAIR 2
#define PPOS 1
#define PPOS0 1
#define NOBW 0
#define CPA 0
#define PFW 0
#define FD0 0
#define FD1 3
#define RPACE 0x221100
#define XA 0
#define XB 4
#define XMMA 1
namespace {

constexpr int S_LEN = 2048, D_MODEL = 1024;
constexpr int NAUX = 4, NMAIN = 128;
constexpr int SLOT = 16384;
constexpr int QST = 24576;
constexpr int OFF_RA = 6 * SLOT, OFF_S = 10 * SLOT;
constexpr int OFF_HALO = 13 * SLOT, OFF_LNB = OFF_HALO  , OFF_ONES = OFF_HALO + 3072;
constexpr int OFF_ST = OFF_HALO + 7168  , OFF_ID = OFF_HALO + 7680, OFF_PHI = OFF_HALO + 8192;
constexpr int OFF_BAR = 14 * SLOT;
constexpr int OFF_LNA = OFF_BAR + 1024;
constexpr int SMEM_BYTES = OFF_LNA + 2048;
#define WO_ASLOT(par) ((par) ? 0x9876CAB39876CA98ull : 0x98C76BA398C7698Cull)
constexpr unsigned long long WO_BSLOT = 0x5432105421054210ull;
__device__ __forceinline__ int srcb(int j, int i) { return (i + (i >= j)) & 7; }
__device__ __forceinline__ int kslice(int j, int i) { return i < 2 ? 2 * j + i : (i < 9 ? 2 * srcb(j, i - 2) : 2 * srcb(j, i - 9) + 1); }
__device__ __forceinline__ int wslice(int j, int s) { return 2 * ((s & 7) ? srcb(j, (s & 7) - 1) : j) + (s >> 3); }
constexpr int KVH = 6 * 128 * 4;

struct __align__(128) Flag { unsigned v; unsigned pad[31]; };
struct Flags {
  Flag xready[4][16];
  Flag wfready[8];
  Flag done;
  Flag epoch;
};

__device__ Flags g_flags;
__device__ __nv_bfloat16 g_obuf[2 * S_LEN * D_MODEL];
#define O_BIT(l) ((epoch * NLAYERS + (l) + 1) & 1u)
#define X_BIT(l) ((epoch * (NLAYERS - 1) + (l) + 1) & 1u)
__device__ __nv_bfloat16 g_wfold[D_MODEL * 2048];
__device__ uint4 g_halo[16 * 8 * 512];
__device__ __align__(128) float g_kv[2][32 * KVH];
__device__ __align__(128) uint2 g_colsum[2][1536][2];
__device__ __align__(128) uint2 g_stats[S_LEN * 8];
#define H_BIT(l) (NLAYERS > 2 ? (uint32_t)((l) == 0) : (ep1 & 1))
#define STAT_TAG(l) ((ep1 * NLAYERS + (l) + 1) & 3u)

#define RETRY_COUNT()
#define PRL 0
#define PRU 0
#define PROFL 1
#define PROFW 0
#define PROFT(i) do {} while (0)
#define PROF(i) do {} while (0)
#define PROFH(i, j) do {} while (0)

__device__ __forceinline__ uint32_t smem_u32(const void* p) { return (uint32_t)__cvta_generic_to_shared(p); }
__device__ __forceinline__ bool elect_one() {
  uint32_t p;
  asm volatile("{\n.reg .pred p;\nelect.sync _|p, 0xffffffff;\nselp.u32 %0, 1, 0, p;\n}\n" : "=r"(p));
  return p != 0;
}
__device__ __forceinline__ void mbar_init(uint32_t bar, uint32_t cnt) {
  asm volatile("mbarrier.init.shared::cta.b64 [%0], %1;" :: "r"(bar), "r"(cnt));
}
__device__ __forceinline__ void mbar_expect_tx(uint32_t bar, uint32_t bytes) {
  asm volatile("mbarrier.arrive.expect_tx.shared::cta.b64 _, [%0], %1;" :: "r"(bar), "r"(bytes) : "memory");
}
#define mbar_wait(bar, parity) \
  asm volatile("{\n.reg .pred p, q;\nW_%=:\nmbarrier.try_wait.parity.shared::cta.b64 p, [%1], %2;\nadd.s32 %0, %0, -1;\n" \
               "setp.gt.and.s32 q, %0, 0, !p;\n@q bra.uni W_%=;\n}\n" : "+r"(budget) : "r"((uint32_t)(bar)), "r"((uint32_t)(parity)) : "memory")
#define mbar_wait_sl(bar, parity) \
  asm volatile("{\n.reg .pred p, q;\nW_%=:\nmbarrier.try_wait.parity.shared::cta.b64 p, [%1], %2, 20000;\nadd.s32 %0, %0, -64;\n" \
               "setp.gt.and.s32 q, %0, 0, !p;\n@q bra.uni W_%=;\n}\n" : "+r"(budget) : "r"((uint32_t)(bar)), "r"((uint32_t)(parity)) : "memory")
__device__ __forceinline__ void mbar_arrive_local(uint32_t bar) {
  asm volatile("mbarrier.arrive.shared::cta.b64 _, [%0];" :: "r"(bar) : "memory");
}
__device__ __forceinline__ void tma_load_2d(uint32_t dst, const CUtensorMap* tm, uint32_t bar, int c0, int c1) {
  asm volatile("cp.async.bulk.tensor.2d.shared::cluster.global.mbarrier::complete_tx::bytes [%0], [%1, {%3, %4}], [%2];"
               :: "r"(dst), "l"(tm), "r"(bar), "r"(c0), "r"(c1) : "memory");
}
__device__ __forceinline__ void tma_load_2d_mc(uint32_t dst, const CUtensorMap* tm, uint32_t bar, int c0, int c1) {
  asm volatile("cp.async.bulk.tensor.2d.shared::cluster.global.mbarrier::complete_tx::bytes.multicast::cluster [%0], [%1, {%3, %4}], [%2], %5;"
               :: "r"(dst), "l"(tm), "r"(bar), "r"(c0), "r"(c1), "h"((uint16_t)3) : "memory");
}
__device__ __forceinline__ void tma_store_2d(const CUtensorMap* tm, uint32_t src, int c0, int c1) {
  asm volatile("cp.async.bulk.tensor.2d.global.shared::cta.bulk_group [%0, {%2, %3}], [%1];"
               :: "l"(tm), "r"(src), "r"(c0), "r"(c1) : "memory");
}
__device__ __forceinline__ void bulk_commit_wait() {
  asm volatile("cp.async.bulk.commit_group;\ncp.async.bulk.wait_group 0;" ::: "memory");
}
__device__ __forceinline__ void prefetch_tmap(const CUtensorMap* tm) {
  asm volatile("prefetch.tensormap [%0];" :: "l"(tm) : "memory");
}
__device__ __forceinline__ void fence_proxy_async_global() { asm volatile("fence.proxy.async.global;" ::: "memory"); }
__device__ __forceinline__ void fence_proxy_async_smem() { asm volatile("fence.proxy.async.shared::cta;" ::: "memory"); }
__device__ __forceinline__ unsigned ld_relaxed(const unsigned* p) {
  unsigned v;
  asm volatile("ld.relaxed.gpu.global.u32 %0, [%1];" : "=r"(v) : "l"(p) : "memory");
  return v;
}
__device__ __forceinline__ void fence_acquire() { asm volatile("fence.acquire.gpu;" ::: "memory"); }
__device__ __forceinline__ void wait_flag(const unsigned* p, unsigned target) {
  int it = 0;
  while ((int)(ld_relaxed(p) - target) < 0 && ++it < (1 << 20)) {}
  fence_acquire();
}
__device__ __forceinline__ void signal_release(unsigned* p) {
  asm volatile("red.release.gpu.global.add.u32 [%0], 1;" :: "l"(p) : "memory");
}
template <int ID, int N> __device__ __forceinline__ void bar_arrive() { asm volatile("bar.arrive %0, %1;" :: "n"(ID), "n"(N) : "memory"); }
template <int ID, int N> __device__ __forceinline__ void bar_sync() { asm volatile("bar.sync %0, %1;" :: "n"(ID), "n"(N) : "memory"); }
__device__ __forceinline__ void bar_wg(int wg) { asm volatile("bar.sync %0, 128;" :: "r"(2 + wg) : "memory"); }
__device__ __forceinline__ void cluster_sync() {
  asm volatile("barrier.cluster.arrive.relaxed.aligned;\nbarrier.cluster.wait.aligned;" ::: "memory");
}
__device__ __forceinline__ void cluster_wait() { asm volatile("barrier.cluster.wait.acquire.aligned;" ::: "memory"); }
enum { BAR_X1 = 7, BAR_WF = 8  , BAR_SKEW = 10 };

__device__ __forceinline__ void wgmma_fence() { asm volatile("wgmma.fence.sync.aligned;" ::: "memory"); }
__device__ __forceinline__ void wgmma_commit() { asm volatile("wgmma.commit_group.sync.aligned;" ::: "memory"); }
template <int N> __device__ __forceinline__ void wgmma_wait() { asm volatile("wgmma.wait_group.sync.aligned %0;" :: "n"(N) : "memory"); }

template <int scale_d, int tnsp_b = 1> __device__ __forceinline__ void wgmma_n192(float* d, uint64_t descA, uint64_t descB) {
  asm volatile("{\n.reg .pred p;\nsetp.ne.b32 p, %98, 0;\n"
               "wgmma.mma_async.sync.aligned.m64n192k16.f32.bf16.bf16 {%0,%1,%2,%3,%4,%5,%6,%7,%8,%9,%10,%11,%12,%13,%14,%15,%16,%17,%18,%19,%20,%21,%22,%23,%24,%25,%26,%27,%28,%29,%30,%31,%32,%33,%34,%35,%36,%37,%38,%39,%40,%41,%42,%43,%44,%45,%46,%47,%48,%49,%50,%51,%52,%53,%54,%55,%56,%57,%58,%59,%60,%61,%62,%63,%64,%65,%66,%67,%68,%69,%70,%71,%72,%73,%74,%75,%76,%77,%78,%79,%80,%81,%82,%83,%84,%85,%86,%87,%88,%89,%90,%91,%92,%93,%94,%95}, %96, %97, p, 1, 1, 0, %99;\n}\n"
               : "+f"(d[0]), "+f"(d[1]), "+f"(d[2]), "+f"(d[3]), "+f"(d[4]), "+f"(d[5]), "+f"(d[6]), "+f"(d[7]), "+f"(d[8]), "+f"(d[9]), "+f"(d[10]), "+f"(d[11]), "+f"(d[12]), "+f"(d[13]), "+f"(d[14]), "+f"(d[15]), "+f"(d[16]), "+f"(d[17]), "+f"(d[18]), "+f"(d[19]), "+f"(d[20]), "+f"(d[21]), "+f"(d[22]), "+f"(d[23]), "+f"(d[24]), "+f"(d[25]), "+f"(d[26]), "+f"(d[27]), "+f"(d[28]), "+f"(d[29]), "+f"(d[30]), "+f"(d[31]), "+f"(d[32]), "+f"(d[33]), "+f"(d[34]), "+f"(d[35]), "+f"(d[36]), "+f"(d[37]), "+f"(d[38]), "+f"(d[39]), "+f"(d[40]), "+f"(d[41]), "+f"(d[42]), "+f"(d[43]), "+f"(d[44]), "+f"(d[45]), "+f"(d[46]), "+f"(d[47]), "+f"(d[48]), "+f"(d[49]), "+f"(d[50]), "+f"(d[51]), "+f"(d[52]), "+f"(d[53]), "+f"(d[54]), "+f"(d[55]), "+f"(d[56]), "+f"(d[57]), "+f"(d[58]), "+f"(d[59]), "+f"(d[60]), "+f"(d[61]), "+f"(d[62]), "+f"(d[63]), "+f"(d[64]), "+f"(d[65]), "+f"(d[66]), "+f"(d[67]), "+f"(d[68]), "+f"(d[69]), "+f"(d[70]), "+f"(d[71]), "+f"(d[72]), "+f"(d[73]), "+f"(d[74]), "+f"(d[75]), "+f"(d[76]), "+f"(d[77]), "+f"(d[78]), "+f"(d[79]), "+f"(d[80]), "+f"(d[81]), "+f"(d[82]), "+f"(d[83]), "+f"(d[84]), "+f"(d[85]), "+f"(d[86]), "+f"(d[87]), "+f"(d[88]), "+f"(d[89]), "+f"(d[90]), "+f"(d[91]), "+f"(d[92]), "+f"(d[93]), "+f"(d[94]), "+f"(d[95])
               : "l"(descA), "l"(descB), "n"(scale_d), "n"(tnsp_b));
}
template <int scale_d> __device__ __forceinline__ void wgmma4_n192(float* d, uint32_t da, uint32_t db) {
#define R_ "{%0,%1,%2,%3,%4,%5,%6,%7,%8,%9,%10,%11,%12,%13,%14,%15,%16,%17,%18,%19,%20,%21,%22,%23,%24,%25,%26,%27,%28,%29,%30,%31,%32,%33,%34,%35,%36,%37,%38,%39,%40,%41,%42,%43,%44,%45,%46,%47,%48,%49,%50,%51,%52,%53,%54,%55,%56,%57,%58,%59,%60,%61,%62,%63,%64,%65,%66,%67,%68,%69,%70,%71,%72,%73,%74,%75,%76,%77,%78,%79,%80,%81,%82,%83,%84,%85,%86,%87,%88,%89,%90,%91,%92,%93,%94,%95}"
  asm volatile("{\n.reg .pred p, q;\n.reg .b64 a, b;\nsetp.ne.b32 p, %98, 0;\nsetp.eq.b32 q, 0, 0;\nmov.b64 a, {%96, 0x40000040};\nmov.b64 b, {%97, 0x40000040};\n"
               "wgmma.mma_async.sync.aligned.m64n192k16.f32.bf16.bf16 " R_ ", a, b, p, 1, 1, 0, 1;\nadd.s64 a, a, 2;\nadd.s64 b, b, 128;\n"
               "wgmma.mma_async.sync.aligned.m64n192k16.f32.bf16.bf16 " R_ ", a, b, q, 1, 1, 0, 1;\nadd.s64 a, a, 2;\nadd.s64 b, b, 128;\n"
               "wgmma.mma_async.sync.aligned.m64n192k16.f32.bf16.bf16 " R_ ", a, b, q, 1, 1, 0, 1;\nadd.s64 a, a, 2;\nadd.s64 b, b, 128;\n"
               "wgmma.mma_async.sync.aligned.m64n192k16.f32.bf16.bf16 " R_ ", a, b, q, 1, 1, 0, 1;\n}\n"
               : "+f"(d[0]), "+f"(d[1]), "+f"(d[2]), "+f"(d[3]), "+f"(d[4]), "+f"(d[5]), "+f"(d[6]), "+f"(d[7]), "+f"(d[8]), "+f"(d[9]), "+f"(d[10]), "+f"(d[11]), "+f"(d[12]), "+f"(d[13]), "+f"(d[14]), "+f"(d[15]), "+f"(d[16]), "+f"(d[17]), "+f"(d[18]), "+f"(d[19]), "+f"(d[20]), "+f"(d[21]), "+f"(d[22]), "+f"(d[23]), "+f"(d[24]), "+f"(d[25]), "+f"(d[26]), "+f"(d[27]), "+f"(d[28]), "+f"(d[29]), "+f"(d[30]), "+f"(d[31]), "+f"(d[32]), "+f"(d[33]), "+f"(d[34]), "+f"(d[35]), "+f"(d[36]), "+f"(d[37]), "+f"(d[38]), "+f"(d[39]), "+f"(d[40]), "+f"(d[41]), "+f"(d[42]), "+f"(d[43]), "+f"(d[44]), "+f"(d[45]), "+f"(d[46]), "+f"(d[47]), "+f"(d[48]), "+f"(d[49]), "+f"(d[50]), "+f"(d[51]), "+f"(d[52]), "+f"(d[53]), "+f"(d[54]), "+f"(d[55]), "+f"(d[56]), "+f"(d[57]), "+f"(d[58]), "+f"(d[59]), "+f"(d[60]), "+f"(d[61]), "+f"(d[62]), "+f"(d[63]), "+f"(d[64]), "+f"(d[65]), "+f"(d[66]), "+f"(d[67]), "+f"(d[68]), "+f"(d[69]), "+f"(d[70]), "+f"(d[71]), "+f"(d[72]), "+f"(d[73]), "+f"(d[74]), "+f"(d[75]), "+f"(d[76]), "+f"(d[77]), "+f"(d[78]), "+f"(d[79]), "+f"(d[80]), "+f"(d[81]), "+f"(d[82]), "+f"(d[83]), "+f"(d[84]), "+f"(d[85]), "+f"(d[86]), "+f"(d[87]), "+f"(d[88]), "+f"(d[89]), "+f"(d[90]), "+f"(d[91]), "+f"(d[92]), "+f"(d[93]), "+f"(d[94]), "+f"(d[95])
               : "r"(da), "r"(db), "n"(scale_d));
#undef R_
}
template <int scale_d> __device__ __forceinline__ void wgmma4_n128(float* d, uint32_t da, uint32_t db) {
#define R_ "{%0,%1,%2,%3,%4,%5,%6,%7,%8,%9,%10,%11,%12,%13,%14,%15,%16,%17,%18,%19,%20,%21,%22,%23,%24,%25,%26,%27,%28,%29,%30,%31,%32,%33,%34,%35,%36,%37,%38,%39,%40,%41,%42,%43,%44,%45,%46,%47,%48,%49,%50,%51,%52,%53,%54,%55,%56,%57,%58,%59,%60,%61,%62,%63}"
  asm volatile("{\n.reg .pred p, q;\n.reg .b64 a, b;\nsetp.ne.b32 p, %66, 0;\nsetp.eq.b32 q, 0, 0;\nmov.b64 a, {%64, 0x40000040};\nmov.b64 b, {%65, 0x40000040};\n"
               "wgmma.mma_async.sync.aligned.m64n128k16.f32.bf16.bf16 " R_ ", a, b, p, 1, 1, 0, 1;\nadd.s64 a, a, 2;\nadd.s64 b, b, 128;\n"
               "wgmma.mma_async.sync.aligned.m64n128k16.f32.bf16.bf16 " R_ ", a, b, q, 1, 1, 0, 1;\nadd.s64 a, a, 2;\nadd.s64 b, b, 128;\n"
               "wgmma.mma_async.sync.aligned.m64n128k16.f32.bf16.bf16 " R_ ", a, b, q, 1, 1, 0, 1;\nadd.s64 a, a, 2;\nadd.s64 b, b, 128;\n"
               "wgmma.mma_async.sync.aligned.m64n128k16.f32.bf16.bf16 " R_ ", a, b, q, 1, 1, 0, 1;\n}\n"
               : "+f"(d[0]), "+f"(d[1]), "+f"(d[2]), "+f"(d[3]), "+f"(d[4]), "+f"(d[5]), "+f"(d[6]), "+f"(d[7]), "+f"(d[8]), "+f"(d[9]), "+f"(d[10]), "+f"(d[11]), "+f"(d[12]), "+f"(d[13]), "+f"(d[14]), "+f"(d[15]), "+f"(d[16]), "+f"(d[17]), "+f"(d[18]), "+f"(d[19]), "+f"(d[20]), "+f"(d[21]), "+f"(d[22]), "+f"(d[23]), "+f"(d[24]), "+f"(d[25]), "+f"(d[26]), "+f"(d[27]), "+f"(d[28]), "+f"(d[29]), "+f"(d[30]), "+f"(d[31]), "+f"(d[32]), "+f"(d[33]), "+f"(d[34]), "+f"(d[35]), "+f"(d[36]), "+f"(d[37]), "+f"(d[38]), "+f"(d[39]), "+f"(d[40]), "+f"(d[41]), "+f"(d[42]), "+f"(d[43]), "+f"(d[44]), "+f"(d[45]), "+f"(d[46]), "+f"(d[47]), "+f"(d[48]), "+f"(d[49]), "+f"(d[50]), "+f"(d[51]), "+f"(d[52]), "+f"(d[53]), "+f"(d[54]), "+f"(d[55]), "+f"(d[56]), "+f"(d[57]), "+f"(d[58]), "+f"(d[59]), "+f"(d[60]), "+f"(d[61]), "+f"(d[62]), "+f"(d[63])
               : "r"(da), "r"(db), "n"(scale_d));
#undef R_
}
template <int scale_d> __device__ __forceinline__ void wgmma_n32(float* d, uint64_t descA, uint64_t descB) {
  asm volatile("{\n.reg .pred p;\nsetp.ne.b32 p, %18, 0;\n"
               "wgmma.mma_async.sync.aligned.m64n32k16.f32.bf16.bf16 {%0,%1,%2,%3,%4,%5,%6,%7,%8,%9,%10,%11,%12,%13,%14,%15}, %16, %17, p, 1, 1, 0, 1;\n}\n"
               : "+f"(d[0]), "+f"(d[1]), "+f"(d[2]), "+f"(d[3]), "+f"(d[4]), "+f"(d[5]), "+f"(d[6]), "+f"(d[7]), "+f"(d[8]), "+f"(d[9]), "+f"(d[10]), "+f"(d[11]), "+f"(d[12]), "+f"(d[13]), "+f"(d[14]), "+f"(d[15])
               : "l"(descA), "l"(descB), "n"(scale_d));
}
template <int scale_d> __device__ __forceinline__ void wgmma_n16(float* d, uint64_t descA, uint64_t descB) {
  asm volatile("{\n.reg .pred p;\nsetp.ne.b32 p, %10, 0;\n"
               "wgmma.mma_async.sync.aligned.m64n16k16.f32.bf16.bf16 {%0,%1,%2,%3,%4,%5,%6,%7}, %8, %9, p, 1, 1, 0, 0;\n}\n"
               : "+f"(d[0]), "+f"(d[1]), "+f"(d[2]), "+f"(d[3]), "+f"(d[4]), "+f"(d[5]), "+f"(d[6]), "+f"(d[7])
               : "l"(descA), "l"(descB), "n"(scale_d));
}
template <int scale_d, int tnsp_a> __device__ __forceinline__ void wgmma_n40(float* d, uint64_t descA, uint64_t descB) {
  asm volatile("{\n.reg .pred p;\nsetp.ne.b32 p, %22, 0;\n"
               "wgmma.mma_async.sync.aligned.m64n40k16.f32.bf16.bf16 {%0,%1,%2,%3,%4,%5,%6,%7,%8,%9,%10,%11,%12,%13,%14,%15,%16,%17,%18,%19}, %20, %21, p, 1, 1, %23, 1;\n}\n"
               : "+f"(d[0]), "+f"(d[1]), "+f"(d[2]), "+f"(d[3]), "+f"(d[4]), "+f"(d[5]), "+f"(d[6]), "+f"(d[7]), "+f"(d[8]), "+f"(d[9]), "+f"(d[10]), "+f"(d[11]), "+f"(d[12]), "+f"(d[13]), "+f"(d[14]), "+f"(d[15]), "+f"(d[16]), "+f"(d[17]), "+f"(d[18]), "+f"(d[19])
               : "l"(descA), "l"(descB), "n"(scale_d), "n"(tnsp_a));
}
template <int scale_d> __device__ __forceinline__ void wgmma_n40_rs(float* d, const uint32_t* a, uint64_t descB) {
  asm volatile("{\n.reg .pred p;\nsetp.ne.b32 p, %25, 0;\n"
               "wgmma.mma_async.sync.aligned.m64n40k16.f32.bf16.bf16 {%0,%1,%2,%3,%4,%5,%6,%7,%8,%9,%10,%11,%12,%13,%14,%15,%16,%17,%18,%19}, {%20,%21,%22,%23}, %24, p, 1, 1, 1;\n}\n"
               : "+f"(d[0]), "+f"(d[1]), "+f"(d[2]), "+f"(d[3]), "+f"(d[4]), "+f"(d[5]), "+f"(d[6]), "+f"(d[7]), "+f"(d[8]), "+f"(d[9]), "+f"(d[10]), "+f"(d[11]), "+f"(d[12]), "+f"(d[13]), "+f"(d[14]), "+f"(d[15]), "+f"(d[16]), "+f"(d[17]), "+f"(d[18]), "+f"(d[19])
               : "r"(a[0]), "r"(a[1]), "r"(a[2]), "r"(a[3]), "l"(descB), "n"(scale_d));
}
__device__ __forceinline__ void wgmma_copy(float* d, uint32_t da, uint64_t descB, int keep) {
  asm volatile("{\n.reg .pred p;\n.reg .b64 a;\nsetp.ne.b32 p, %66, 0;\nmov.b64 a, {%64, 0x40000040};\n"
               "wgmma.mma_async.sync.aligned.m64n16k16.f32.bf16.bf16 {%0,%1,%2,%3,%4,%5,%6,%7}, a, %65, p, 1, 1, 0, 0;\nadd.s64 a, a, 2;\n"
               "wgmma.mma_async.sync.aligned.m64n16k16.f32.bf16.bf16 {%8,%9,%10,%11,%12,%13,%14,%15}, a, %65, p, 1, 1, 0, 0;\nadd.s64 a, a, 2;\n"
               "wgmma.mma_async.sync.aligned.m64n16k16.f32.bf16.bf16 {%16,%17,%18,%19,%20,%21,%22,%23}, a, %65, p, 1, 1, 0, 0;\nadd.s64 a, a, 2;\n"
               "wgmma.mma_async.sync.aligned.m64n16k16.f32.bf16.bf16 {%24,%25,%26,%27,%28,%29,%30,%31}, a, %65, p, 1, 1, 0, 0;\nadd.s64 a, a, 1018;\n"
               "wgmma.mma_async.sync.aligned.m64n16k16.f32.bf16.bf16 {%32,%33,%34,%35,%36,%37,%38,%39}, a, %65, p, 1, 1, 0, 0;\nadd.s64 a, a, 2;\n"
               "wgmma.mma_async.sync.aligned.m64n16k16.f32.bf16.bf16 {%40,%41,%42,%43,%44,%45,%46,%47}, a, %65, p, 1, 1, 0, 0;\nadd.s64 a, a, 2;\n"
               "wgmma.mma_async.sync.aligned.m64n16k16.f32.bf16.bf16 {%48,%49,%50,%51,%52,%53,%54,%55}, a, %65, p, 1, 1, 0, 0;\nadd.s64 a, a, 2;\n"
               "wgmma.mma_async.sync.aligned.m64n16k16.f32.bf16.bf16 {%56,%57,%58,%59,%60,%61,%62,%63}, a, %65, p, 1, 1, 0, 0;\n"
               "}\n"
               : "+f"(d[0]), "+f"(d[1]), "+f"(d[2]), "+f"(d[3]), "+f"(d[4]), "+f"(d[5]), "+f"(d[6]), "+f"(d[7]), "+f"(d[8]), "+f"(d[9]), "+f"(d[10]), "+f"(d[11]), "+f"(d[12]), "+f"(d[13]), "+f"(d[14]), "+f"(d[15]), "+f"(d[16]), "+f"(d[17]), "+f"(d[18]), "+f"(d[19]), "+f"(d[20]), "+f"(d[21]), "+f"(d[22]), "+f"(d[23]), "+f"(d[24]), "+f"(d[25]), "+f"(d[26]), "+f"(d[27]), "+f"(d[28]), "+f"(d[29]), "+f"(d[30]), "+f"(d[31]), "+f"(d[32]), "+f"(d[33]), "+f"(d[34]), "+f"(d[35]), "+f"(d[36]), "+f"(d[37]), "+f"(d[38]), "+f"(d[39]), "+f"(d[40]), "+f"(d[41]), "+f"(d[42]), "+f"(d[43]), "+f"(d[44]), "+f"(d[45]), "+f"(d[46]), "+f"(d[47]), "+f"(d[48]), "+f"(d[49]), "+f"(d[50]), "+f"(d[51]), "+f"(d[52]), "+f"(d[53]), "+f"(d[54]), "+f"(d[55]), "+f"(d[56]), "+f"(d[57]), "+f"(d[58]), "+f"(d[59]), "+f"(d[60]), "+f"(d[61]), "+f"(d[62]), "+f"(d[63])
               : "r"(da), "l"(descB), "r"(keep));
}
__device__ __forceinline__ uint64_t make_desc(uint32_t addr, uint32_t lbo_bytes, uint32_t sbo_bytes) {
  return (uint64_t)((addr & 0x3FFFF) >> 4) | ((uint64_t)(lbo_bytes >> 4) << 16) | ((uint64_t)(sbo_bytes >> 4) << 32) | (1ull << 62);
}

__device__ __forceinline__ void ldsm_x4(uint32_t addr, uint32_t& r0, uint32_t& r1, uint32_t& r2, uint32_t& r3) {
  asm volatile("ldmatrix.sync.aligned.m8n8.x4.shared.b16 {%0,%1,%2,%3}, [%4];" : "=r"(r0), "=r"(r1), "=r"(r2), "=r"(r3) : "r"(addr) : "memory");
}
__device__ __forceinline__ void ldsm_x4_t(uint32_t addr, uint32_t& r0, uint32_t& r1, uint32_t& r2, uint32_t& r3) {
  asm volatile("ldmatrix.sync.aligned.m8n8.x4.trans.shared.b16 {%0,%1,%2,%3}, [%4];" : "=r"(r0), "=r"(r1), "=r"(r2), "=r"(r3) : "r"(addr) : "memory");
}
__device__ __forceinline__ void stsm_x4(uint32_t addr, uint32_t r0, uint32_t r1, uint32_t r2, uint32_t r3) {
  asm volatile("stmatrix.sync.aligned.m8n8.x4.shared.b16 [%0], {%1,%2,%3,%4};" :: "r"(addr), "r"(r0), "r"(r1), "r"(r2), "r"(r3) : "memory");
}
__device__ __forceinline__ void sts128(uint32_t addr, uint32_t a, uint32_t b, uint32_t c, uint32_t d) {
  asm volatile("st.shared.v4.u32 [%0], {%1,%2,%3,%4};" :: "r"(addr), "r"(a), "r"(b), "r"(c), "r"(d) : "memory");
}
__device__ __forceinline__ float lds32f(uint32_t addr) {
  float v;
  asm volatile("ld.shared.f32 %0, [%1];" : "=f"(v) : "r"(addr) : "memory");
  return v;
}
__device__ __forceinline__ void sts32f(uint32_t addr, float a) {
  asm volatile("st.shared.f32 [%0], %1;" :: "r"(addr), "f"(a) : "memory");
}
__device__ __forceinline__ void mma_bf16(float (&c)[4], uint32_t a0, uint32_t a1, uint32_t a2, uint32_t a3, uint32_t b0, uint32_t b1) {
  asm volatile("mma.sync.aligned.m16n8k16.row.col.f32.bf16.bf16.f32 {%0,%1,%2,%3}, {%4,%5,%6,%7}, {%8,%9}, {%0,%1,%2,%3};"
               : "+f"(c[0]), "+f"(c[1]), "+f"(c[2]), "+f"(c[3]) : "r"(a0), "r"(a1), "r"(a2), "r"(a3), "r"(b0), "r"(b1));
}
__device__ __forceinline__ void mma_bf16_z(float (&c)[4], uint32_t a0, uint32_t a1, uint32_t a2, uint32_t a3, uint32_t b0, uint32_t b1) {
  asm volatile("mma.sync.aligned.m16n8k16.row.col.f32.bf16.bf16.f32 {%0,%1,%2,%3}, {%4,%5,%6,%7}, {%8,%9}, {%10,%10,%10,%10};"
               : "=f"(c[0]), "=f"(c[1]), "=f"(c[2]), "=f"(c[3]) : "r"(a0), "r"(a1), "r"(a2), "r"(a3), "r"(b0), "r"(b1), "f"(0.f));
}
__device__ __forceinline__ uint32_t movm_t(uint32_t v) {
  uint32_t r;
  asm volatile("movmatrix.sync.aligned.m8n8.trans.b16 %0, %1;" : "=r"(r) : "r"(v));
  return r;
}
__device__ __forceinline__ uint32_t pack_bf16(float lo, float hi) {
  uint32_t r;
  asm("cvt.rn.bf16x2.f32 %0, %1, %2;" : "=r"(r) : "f"(hi), "f"(lo));
  return r;
}
__device__ __forceinline__ float bf_lo(uint32_t v) { return __uint_as_float(v << 16); }
__device__ __forceinline__ float bf_hi(uint32_t v) { return __uint_as_float(v & 0xFFFF0000u); }
__device__ __forceinline__ void split3(float x, uint32_t& h, uint32_t& m, uint32_t& l) {
  h = pack_bf16(x, 0.f); x -= bf_lo(h);
  m = pack_bf16(x, 0.f); x -= bf_lo(m);
  l = pack_bf16(x, 0.f);
}
__device__ __forceinline__ float ex2(float x) { float r; asm("ex2.approx.ftz.f32 %0, %1;" : "=f"(r) : "f"(x)); return r; }
__device__ __forceinline__ float rcp_fast(float x) { float r; asm("rcp.approx.ftz.f32 %0, %1;" : "=f"(r) : "f"(x)); return r; }
__device__ __forceinline__ void red_v4(float* p, float a, float b, float c, float d) {
  asm volatile("red.global.add.v4.f32 [%0], {%1, %2, %3, %4};" :: "l"(p), "f"(a), "f"(b), "f"(c), "f"(d) : "memory");
}
__device__ __forceinline__ uint4 ld_ll(const uint4* p) {
  uint4 v;
  asm volatile("{\n.reg .b64 a, b;\nld.relaxed.gpu.global.v2.b64 {a, b}, [%4];\nmov.b64 {%0, %1}, a;\nmov.b64 {%2, %3}, b;\n}\n"
               : "=r"(v.x), "=r"(v.y), "=r"(v.z), "=r"(v.w) : "l"(p) : "memory");
  return v;
}
__device__ __forceinline__ void st_b64(uint2* p, uint32_t a, uint32_t b) {
  asm volatile("{\n.reg .b64 v;\nmov.b64 v, {%1, %2};\nst.relaxed.gpu.global.b64 [%0], v;\n}\n" :: "l"(p), "r"(a), "r"(b) : "memory");
}
__device__ __forceinline__ void st_b128(uint4* p, uint32_t a, uint32_t b, uint32_t c, uint32_t d) {
  asm volatile("{\n.reg .b128 v;\nmov.b128 v, {%1, %2, %3, %4};\nst.relaxed.gpu.global.b128 [%0], v;\n}\n" :: "l"(p), "r"(a), "r"(b), "r"(c), "r"(d) : "memory");
}
__device__ __forceinline__ uint4 ld_b128(const uint4* p) {
  uint4 v;
  asm volatile("{\n.reg .b128 v;\nld.relaxed.gpu.global.b128 v, [%4];\nmov.b128 {%0, %1, %2, %3}, v;\n}\n" : "=r"(v.x), "=r"(v.y), "=r"(v.z), "=r"(v.w) : "l"(p) : "memory");
  return v;
}

constexpr float LOG2E = 1.4426950408889634f;

struct Params {
  const __nv_bfloat16* x0;
  const __nv_bfloat16* wA_qkv;
  const __nv_bfloat16* wA_o;
  const __nv_bfloat16* wB_qkv;
  const __nv_bfloat16* wB_phi;
  const __nv_bfloat16* wB_o;
  __nv_bfloat16* out;
};

#define ACC_DEF(d, n) _Pragma("unroll") for (int i_ = 0; i_ < (n); i_++) asm volatile("" : "=f"(d[i_]))
#define ACC_FENCE(d, n) _Pragma("unroll") for (int i_ = 0; i_ < (n); i_++) asm volatile("" : "+f"(d[i_]) :: "memory")
#define PIN(a, n) _Pragma("unroll") for (int i_ = 0; i_ < (n); i_++) asm volatile("" : "+f"((a)[i_]))
#define PINU(a, n) _Pragma("unroll") for (int i_ = 0; i_ < (n); i_++) asm volatile("" : "+r"((a)[i_]))

#define V_ADDR(p0) uint32_t va_[2] = {(p0) + (srowoff >> 1) + (lhi ^ lsw2), (p0) + (srowoff >> 1) + ((32 + lhi) ^ lsw2)}
#define STAGE_V(acc) { \
    _Pragma("unroll") for (int j_ = 0; j_ < 4; j_++) { \
      const float* a_ = (acc) + j_ * 8; \
      stsm_x4(va_[j_ & 1] + (j_ >> 1) * 8192, \
              pack_bf16(rs0 * a_[0], rs0 * a_[1]), pack_bf16(rs1 * a_[2], rs1 * a_[3]), pack_bf16(rs0 * a_[4], rs0 * a_[5]), pack_bf16(rs1 * a_[6], rs1 * a_[7])); } }
#define FRAG(dst, acc, TR, grp) { \
    _Pragma("unroll") for (int i_ = 0; i_ < 16; i_++) { \
      const float r_ = (i_ & 1) ? rs1 : rs0; \
      const uint32_t w_ = pack_bf16(r_ * (acc)[2 * i_], r_ * (acc)[2 * i_ + 1]); \
      if (TR) (dst)[i_] = movm_t(w_); else (dst)[(i_ & 12) + (i_ & 1) * 2 + ((i_ >> 1) & 1)] = w_; } \
    if (warp == 7 && mm < 15) { \
      _Pragma("unroll") for (int j_ = 0; j_ < 4; j_++) \
        st_b128(g_halo + (size_t)(mm * 8 + jj) * 512 + ((grp) * 4 + j_) * 32 + lane, ((dst)[j_ * 4] & ~1u) | H_BIT(l), (dst)[j_ * 4 + 1], (dst)[j_ * 4 + 2], (dst)[j_ * 4 + 3]); } \
    PINU(dst, 16); }
#define FRAG_PUT(src, slot) if (warp < 7) { _Pragma("unroll") for (int j_ = 0; j_ < 4; j_++) \
      sts128(sbase + (slot) * SLOT + 2048 + warp * 2048 + j_ * 512 + lane * 16, (src)[j_ * 4], (src)[j_ * 4 + 1], (src)[j_ * 4 + 2], (src)[j_ * 4 + 3]); }
#define FRAG_GET(dst, slot) { _Pragma("unroll") for (int j_ = 0; j_ < 4; j_++) \
      asm volatile("ld.shared.v4.u32 {%0, %1, %2, %3}, [%4];" : "=r"((dst)[j_ * 4]), "=r"((dst)[j_ * 4 + 1]), "=r"((dst)[j_ * 4 + 2]), "=r"((dst)[j_ * 4 + 3]) \
                   : "r"(sbase + (slot) * SLOT + warp * 2048 + j_ * 512 + lane * 16) : "memory"); }
#define RW(j) (((j) >> 1) * 4 + ((j) & 1))
template <int POS> __device__ __forceinline__ float exps16_(float* o, const float* p) {
  float s[4];
#pragma unroll
  for (int j = 0; j < 16; j++) { o[j] = ex2(POS ? p[RW(j)] : -p[RW(j)]); if (j < 4) s[j] = o[j]; else s[j & 3] += o[j]; }
  const float r = (s[0] + s[1]) + (s[2] + s[3]);
  return r + __shfl_xor_sync(0xffffffffu, r, 1);
}
template <int POS> __device__ __forceinline__ void exps16_fix(float* o, const float* p, float& sum) {
  if (__builtin_expect(__any_sync(0xffffffffu, !(sum > SUMLO && sum < SUMHI)), 0)) {
    float m = p[0], q[32];
#pragma unroll
    for (int j = 1; j < 16; j++) m = POS ? fmaxf(m, p[RW(j)]) : fminf(m, p[RW(j)]);
    const float x = __shfl_xor_sync(0xffffffffu, m, 1);
    m = POS ? fmaxf(m, x) : fminf(m, x);
#pragma unroll
    for (int j = 0; j < 16; j++) q[RW(j)] = p[RW(j)] - m;
    sum = exps16_<POS>(o, q);
  }
}
__device__ __forceinline__ void store16(const float* e, float sum, uint32_t dst, uint32_t dsw, int c0) {
  const float inv = rcp_fast(sum);
#pragma unroll
  for (int j = 0; j < 2; j++)
    sts128(dst + (((c0 + j) << 4) ^ dsw), pack_bf16(e[j * 8] * inv, e[j * 8 + 1] * inv), pack_bf16(e[j * 8 + 2] * inv, e[j * 8 + 3] * inv),
           pack_bf16(e[j * 8 + 4] * inv, e[j * 8 + 5] * inv), pack_bf16(e[j * 8 + 6] * inv, e[j * 8 + 7] * inv));
}
template <int POS> __device__ __forceinline__ void expp16(uint32_t* o, float* p) {
  {
#pragma unroll
    for (int r = 0; r < 4; r += 2) {
      float m = p[r];
#pragma unroll
      for (int j = 1; j < 8; j++) m = POS ? fmaxf(m, p[r + RW(j)]) : fminf(m, p[r + RW(j)]);
#pragma unroll
      for (int s = 1; s <= 2; s <<= 1) { const float x = __shfl_xor_sync(0xffffffffu, m, s); m = POS ? fmaxf(m, x) : fminf(m, x); }
#pragma unroll
      for (int j = 0; j < 8; j++) p[r + RW(j)] -= m;
    }
  }
#pragma unroll
  for (int j = 0; j < 8; j++) o[j] = pack_bf16(ex2(POS ? p[2 * j] : -p[2 * j]), ex2(POS ? p[2 * j + 1] : -p[2 * j + 1]));
}
__device__ __forceinline__ void scale32(float* o, const float* p, float c0, float c1) {
#pragma unroll
  for (int i = 0; i < 32; i++) asm volatile("mul.f32 %0, %1, %2;" : "=f"(o[i]) : "f"(p[i]), "f"((i & 2) ? c1 : c0));
}
__device__ __forceinline__ bool any_big(const float* p) {
  float m[4];
#pragma unroll
  for (int i = 0; i < 32; i++) m[i >> 3] = (i & 7) ? fmaf(p[i], p[i], m[i >> 3]) : p[i] * p[i];
  return __any_sync(0xffffffffu, !(fmaxf(fmaxf(m[0], m[1]), fmaxf(m[2], m[3])) < BIGLIM));
}
__device__ __forceinline__ void phiq_a(float* p, bool big) {
  if (__builtin_expect(!big, 1)) {
#pragma unroll
    for (int j = 0; j < 16; j++) p[j] = ex2(p[j]);
  }
}
template <int NEXT> __device__ __forceinline__ void phiq_b(uint32_t* o, float* p, bool big) {
  if (__builtin_expect(big, 0)) {
    expp16<0>(o, p); expp16<1>(o + 8, p);
  } else {
    if (NEXT) phiq_a(p + 16, false);
#pragma unroll
    for (int j = 0; j < 4; j++) {
      const float a = p[4 * j], b = p[4 * j + 1], c = p[4 * j + 2], d = p[4 * j + 3];
      const float ab = a * b, cd = c * d, r = rcp_fast(ab * cd), x = r * cd, y = r * ab;
      o[2 * j] = pack_bf16(x * b, x * a); o[2 * j + 1] = pack_bf16(y * d, y * c);
      o[8 + 2 * j] = pack_bf16(a, b); o[9 + 2 * j] = pack_bf16(c, d);
    }
  }
}
#define SCHED_FENCE() asm volatile("pmevent 0;" ::: "memory")

__global__ void __cluster_dims__(2, 1, 1) __launch_bounds__(384, 1)
mega_kernel(const __grid_constant__ CUtensorMap tm_x0, const __grid_constant__ CUtensorMap tm_xo, const __grid_constant__ CUtensorMap tm_os,
            const __grid_constant__ CUtensorMap tm_o, const __grid_constant__ CUtensorMap tm_wf,
            const __grid_constant__ CUtensorMap tm_wqA, const __grid_constant__ CUtensorMap tm_wqB,
            const __grid_constant__ CUtensorMap tm_woA, const __grid_constant__ CUtensorMap tm_woB,
            const __grid_constant__ CUtensorMap tm_phi, const Params prm) {
  extern __shared__ __align__(1024) uint8_t smem_raw[];
  const uint32_t sbase = smem_u32(smem_raw);
  const uint32_t bar_full = sbase + OFF_BAR;
  const uint32_t bar_done = bar_full + 384;
  const uint32_t bar_stat = bar_full + 768, bar_stat2 = bar_full + 776, bar_epi = bar_full + 784, bar_phi = bar_full + 936  , bar_halo = bar_full + 904  ;
  const uint32_t bar_xr = bar_full + 800, bar_lx = bar_full + 808, bar_stg = bar_full + 832;
  const uint32_t bar_chk = bar_full + 848;

  const int warp = __shfl_sync(0xffffffffu, threadIdx.x >> 5, 0), lane = threadIdx.x & 31;
  const uint32_t bar_kx = sbase + OFF_ID + 384 + warp * 8;
  uint32_t rank;
  asm volatile("mov.u32 %0, %%cluster_ctarank;" : "=r"(rank));
  const int aux = (int)blockIdx.x - NMAIN, tp = (int)(blockIdx.x >> 1) - 4;
  const int gp = tp < 0 ? 0 : (tp < 32 ? tp & 7 : 1 + (tp - 32) % 7), me = tp < 0 ? tp + 8 : (tp < 32 ? tp >> 3 : 4 + (tp - 32) / 7);
  const int jj = me, cc = gp;
  const int cta = aux >= 0 ? -1 : (cc * 8 + jj) * 2 + (int)rank;
  const int mm = cc * 2 + (int)rank;

#define LOAD_EPOCH() const unsigned epoch = ld_relaxed(&g_flags.epoch.v), ep1 = epoch + 1; (void)epoch
  int budget = 1 << 22;

  if (cta >= 0) {
    if (warp >= 8 + CPA && warp < 8 + EARLY && elect_one()) {
      const int u = warp - 8;
      const uint32_t fb = bar_full + u * 8;
      mbar_init(fb, 1);
      asm volatile("fence.mbarrier_init.release.cluster;" ::: "memory");
      fence_proxy_async_smem();
      mbar_expect_tx(fb, UPS(u) ? QST : QST + SLOT);
      if (u) __nanosleep(UPS(u) ? STAG1 : STAG2);
      if (!UPS(u)) tma_load_2d(sbase + OFF_S + USL(u) * SLOT, &tm_x0, fb, jj * 128 + USL(u) * 64, mm * 128);
#pragma unroll
      for (int i = 0; i < 6; i++) tma_load_2d(sbase + u * QST + i * 4096, &tm_wqA, fb, jj * 128 + UPS(u) * 64 + (i >> 1) * 1024, jj * 128 + USL(u) * 64 + (i & 1) * 32);
      if (u == 0) PROFT(472);
    }
    __syncwarp();
    {
      const int tx = threadIdx.x;
      const __nv_bfloat16* pf = (tx < 128) ? prm.x0 + (size_t)(mm * 128 + tx) * D_MODEL + jj * 128
                                           : prm.wA_qkv + (size_t)(jj * 128 + (tx & 63)) * 3072 + ((tx - 128) >> 6) * 1024 + jj * 128 + rank * 64;
      if (tx < 320) { if (PF0 && !CPA) asm volatile("prefetch.global.L2 [%0];" :: "l"(pf)); }
      if (PFW && tx < 24 * PFW) {
        const int q = tx % 24;
        asm volatile("prefetch.global.L2 [%0];" :: "l"(prm.wA_qkv + (size_t)(kslice(jj, 2 + tx / 24) * 64 + mm * 4 + q / 6) * 3072 + (q % 6 >> 1) * 1024 + jj * 128 + (q & 1) * 64));
      }
      if (tx == 320) prefetch_tmap(&tm_x0);
      else if (tx == 352) prefetch_tmap(&tm_wqA);
      else if (tx == 383) asm volatile("prefetch.global.L2 [%0];" :: "l"(&g_flags.epoch.v));
    }
    if (elect_one()) {
#pragma unroll
      for (int i = 0; i < 4; i++) {
        const int u = warp * 4 + i;
        if (u >= EARLY || u < CPA) mbar_init(bar_full + u * 8, ((u >= 4 && u < 11) || (u > 32 && u != 40)) ? 2 : 1); mbar_init(bar_done + u * 8, 16);
      }
      mbar_init(bar_stat + warp * 16, 0x111111181182ull >> (4 * warp) & 15);
      mbar_init(bar_stat + warp * 16 + 8, 0x111111121811ull >> (4 * warp) & 15);
      mbar_init(bar_chk + 112 + (warp & 7) * 8, 1);
      if (PAIR) mbar_init(bar_kx, 1);
      asm volatile("fence.mbarrier_init.release.cluster;" ::: "memory");
    }
    __syncwarp();
    __syncthreads();
    asm volatile("barrier.cluster.arrive.relaxed.aligned;" ::: "memory");
  }

  if (cta < 0) {
    LOAD_EPOCH();
    const uint32_t buf = sbase + warp * SLOT, bar = sbase + OFF_BAR + warp * 16;
    const uint32_t lsw = (lane & 7) << 4, lhi = (lane >> 4) << 4, lrow = (lane & 15) * 128;
    const bool el = elect_one();
    if (el) {
      mbar_init(bar, 1); mbar_init(bar + 8, 1);
      asm volatile("fence.mbarrier_init.release.cluster;" ::: "memory");
    }
#pragma unroll 1
    for (int rd = 0; rd < (NLAYERS > 1 ? 5 : 2); rd++) {
      if (rd >= 2 && warp >= 8) break;
      const int tk = rd < 2 ? aux * 12 + warp : aux * 8 + warp;
      const int half = tk & 1;
      const int blk = rd < 2 ? (tk >> 1) * 2 + rd : (4 - rd) * 16 + (tk >> 1);
      const CUtensorMap* tm = rd < 2 ? &tm_wqA : (rd == 2 ? &tm_wqB : &tm_wf);
      const int j0 = (blk & 15) >> 1;
#define AUX_LOAD(n) { const uint32_t d_ = buf + ((n) & 1) * 8192, b_ = bar + ((n) & 1) * 8; const int r_ = kslice(j0, 2 * (n) + half) * 64; \
        mbar_expect_tx(b_, 8192); tma_load_2d(d_, tm, b_, blk * 64, r_); tma_load_2d(d_ + 4096, tm, b_, blk * 64, r_ + 32); }
      if (el) {
        if (rd == 3) { wait_flag(&g_flags.wfready[j0].v, ep1 * 16); fence_proxy_async_global(); }
        AUX_LOAD(0); AUX_LOAD(1);
      }
      __syncwarp();
      float cs[8][4];
#pragma unroll
      for (int i = 0; i < 8; i++) cs[i][0] = cs[i][1] = cs[i][2] = cs[i][3] = 0.f;
#pragma unroll 1
      for (int n = 0; n < 8; n++) {
        const uint32_t tb = buf + (n & 1) * 8192 + lrow;
        mbar_wait(bar + (n & 1) * 8, (n >> 1) & 1);
#pragma unroll
        for (int i = 0; i < 16; i++) {
          uint32_t b0, b1, b2, b3;
          ldsm_x4_t(tb + (i >> 2) * 2048 + (((i & 3) * 32 + lhi) ^ lsw), b0, b1, b2, b3);
          mma_bf16(cs[2 * (i & 3)], 0x3F803F80u, 0x3F803F80u, 0x3F803F80u, 0x3F803F80u, b0, b1);
          mma_bf16(cs[2 * (i & 3) + 1], 0x3F803F80u, 0x3F803F80u, 0x3F803F80u, 0x3F803F80u, b2, b3);
        }
        __syncwarp();
        if (el && n < 6) AUX_LOAD(n + 2);
        __syncwarp();
      }
      if (lane < 4) {
#pragma unroll
        for (int i = 0; i < 8; i++) st_b64(&g_colsum[rd >= 2][blk * 32 + i * 4 + lane][half], __float_as_uint(cs[i][0]), (__float_as_uint(cs[i][1]) & ~3u) | (ep1 & 3));
      }
      __syncwarp();
    }
  } else if (warp >= 8) {
    asm volatile("setmaxnreg.dec.sync.aligned.u32 40;");
    if (warp == 8) {
      const bool el = elect_one();
      cluster_wait();
      if (el) {
#pragma unroll 1
        for (int l = 0; l < NLAYERS; l++) {
          const uint32_t par = l & 1;
          const CUtensorMap* tqk = par ? &tm_wf : &tm_wqA;
          const CUtensorMap* tv = par ? &tm_wqB : &tm_wqA;
          const CUtensorMap* two = par ? &tm_woB : &tm_woA;
          if (l == 1) { LOAD_EPOCH(); wait_flag(&g_flags.wfready[jj].v, ep1 * 16); fence_proxy_async_global(); }
#pragma unroll 1
          for (int u = l ? 0 : EARLY; u < 32; u++) {
            if (u >= 4) mbar_wait_sl(bar_done + (u - 4) * 8, par);
            else if (l) mbar_wait_sl(bar_done + (43 + u + (u >> 1)) * 8, par ^ 1);
            else if (!W23) mbar_wait_sl(bar_full, 0);
            const uint32_t fb = bar_full + u * 8;
            const bool res = u < 11 || (u >= 18 && u < 22);
            mbar_expect_tx(fb, res ? QST : QST + SLOT);
            const int row = kslice(jj, u < 4 ? USL(u) : (u < 18 ? u - 2 : (u < 22 ? u - 6 : u - 20))) * 64 + (int)rank * 32;
            const int ps = u < 4 ? UPS(u) : (u >= 18), col = jj * 128 + ps * 64;
            const int c0 = par ? jj * 128 + (ps ? 0 : 1024) : col;
            const uint32_t dst = sbase + (u & 3) * QST + rank * 4096;
            tma_load_2d_mc(dst, tqk, fb, c0, row);
            tma_load_2d_mc(dst + 8192, tqk, fb, c0 + (par ? 64 : 1024), row);
            tma_load_2d_mc(dst + 16384, tv, fb, col + 2048, row);
            if (l == PRL && u >= PRU && u < PRU + 4) PROFT(473 + u - PRU);
          }
#pragma unroll 1
          for (int s = 0; s < 16; s++) {
            if (s < 5) { if (s != 2 && s != 4) mbar_wait_sl(bar_done + (28 + s) * 8, par); }
            else if (s != 14) mbar_wait_sl(bar_done + (27 + s - (s == 15)) * 8, par);
            const uint32_t fb = bar_full + (32 + s) * 8;
            mbar_expect_tx(fb, SLOT);
            tma_load_2d_mc(sbase + rank * 8192 + (uint32_t)((WO_BSLOT >> (4 * s)) & 15) * SLOT, two, fb, jj * 128 + (int)rank * 64, wslice(jj, s) * 64);
            const int ts = s + par;
            if (s >= 5 && ts < 8) {
              mbar_expect_tx(bar_chk - 8 + ts * 8, SLOT);
              tma_load_2d(sbase + (uint32_t)((WO_ASLOT(par) >> (4 * ts)) & 15) * SLOT, &tm_o, bar_chk - 8 + ts * 8, wslice(jj, ts) * 64, mm * 128);
            }
          }
        }
      }
      __syncwarp();
    } else if (warp == 9) {
      const bool el = elect_one();
      LOAD_EPOCH();
#pragma unroll 1
      for (int lp = 0; lp < 4 * NLAYERS; lp++) {
        const int l = lp >> 2, ph = lp & 3;
        if (ph == 3) continue;
        const uint32_t par = l & 1;
        const unsigned* pp = reinterpret_cast<const unsigned*>(g_obuf + (ph >> 1) * 64 + (size_t)(mm * 128 + (ph ? 0 : S_LEN) + ((lane & 7) | PROWS) * 16 + (jj & 1) * 8) * D_MODEL +
                                                               (jj >> 1) * 16 + srcb(jj, lane >> 3) * 128);
        const CUtensorMap* tm = lp ? &tm_o : &tm_x0;
        const int row = mm * 128 + ((ph || !l) ? 0 : S_LEN);
        const uint32_t bit = ph ? O_BIT(l) : X_BIT(l - 1);
        const uint32_t slots = ph ? (uint32_t)(WO_ASLOT(par) >> (ph * 32 - 28)) : 0x8769876u;
        const unsigned long long fr = ph == 0 ? XPACE : ph == 1 ? (par ? FRB : 0x35351F1Eull) : (par ? 0x27262524232232ull : 0x27262524233232ull);
        uint32_t no = (lp == 0 || (lp & 7) == 1) ? 0 : (ph == 1 ? NOB : (ph ? NO1 : NOX)), v0 = 0, v1 = 0;
        if (lp || !AX) mbar_wait_sl(ph ? bar_done + ((uint32_t)fr & 63) * 8 : (l ? bar_done + 47 * 8 : bar_full), ph ? par : (l ? par ^ 1 : 0));
        if (el && ph) PROFT(324 + l * 16 + ph);
        __syncwarp();
        if (no && (ph == 1 ? SPD1 : (ph ? SPD2 : SPD0))) __nanosleep(ph == 1 ? SPD1 : (ph ? SPD2 : SPD0));
        if (no) { v0 = ld_relaxed(pp); __nanosleep(POLLGAP); v1 = ld_relaxed(pp); }
#pragma unroll 1
        for (int i = 0; i < (ph == 1 ? 4 + par : 7); i++, no >>= 8) {
#pragma unroll 1
          for (int it = 0; (no & 0xFF) && it < (1 << 18); it++) {
            no &= __ballot_sync(0xffffffffu, (v0 ^ bit) & 1) >> (8 * i);
            if (no) v0 = ld_relaxed(pp);
            if (!(no & 0xFF)) break;
            no &= __ballot_sync(0xffffffffu, (v1 ^ bit) & 1) >> (8 * i);
            if (no) v1 = ld_relaxed(pp);
          }
          if (ph || i >= XP0) mbar_wait_sl(bar_done + ((uint32_t)(fr >> (8 * i)) & 63) * 8, par);
          if (el) {
            if (i == 0) PROFT(320 + l * 16 + ph);
            const uint32_t cb = (lp ? bar_chk + (ph >> 1) * 112 : bar_full + 32) + i * 8;
            mbar_expect_tx(cb, SLOT);
            tma_load_2d(sbase + ((slots >> (4 * i)) & 15) * SLOT, tm, cb, srcb(jj, i) * 128 + (ph >> 1) * 64, row);
          }
          __syncwarp();
        }
        if (ph == 0 && el) {
          if (l) { wait_flag(&g_flags.xready[l][mm].v, ep1 * 8); fence_proxy_async_global(); }
#pragma unroll 1
          for (int u = 11; u < 34; u++) {
            if (u == 18) u = 22;
            mbar_wait_sl(bar_done + (u - 4) * 8, par);
            if (u == 32) mbar_expect_tx(bar_xr, 2 * SLOT);
            tma_load_2d(sbase + OFF_RA + (u & 3) * SLOT, tm, u < 32 ? bar_full + u * 8 : bar_xr, kslice(jj, u < 18 ? u - 2 : (u < 32 ? u - 20 : u - 32)) * 64, row);
          }
        }
        __syncwarp();
      }
      if (el && atomicAdd(&g_flags.done.v, 1) == ep1 * NMAIN - 1) asm volatile("st.relaxed.gpu.global.u32 [%0], %1;" :: "l"(&g_flags.epoch.v), "r"(ep1) : "memory");
      __syncwarp();
      cluster_wait();
    } else {
      const int hw = warp - 10;
      LOAD_EPOCH();
      const bool el = elect_one();
      cluster_wait();
      if (hw == 0) {
        mbar_wait_sl(bar_full + 8 + 8 * ORD, 0);
        if (lane < 7) prefetch_tmap(lane == 0 ? &tm_os : lane == 1 ? &tm_o : lane == 2 ? &tm_wf : lane == 3 ? &tm_wqB : lane == 4 ? &tm_woA : lane == 5 ? &tm_woB : &tm_phi);
#pragma unroll 1
        for (int i = 0; i < (NLAYERS > 1 ? 9 : 0); i++) {
          if (i == 0 || i == 5) mbar_wait_sl(bar_done + (i ? FD1 : FD0) * 8, 0);
          if (el) {
            if (i == 0) { mbar_expect_tx(bar_phi, 2 * SLOT + 8192); tma_load_2d(sbase + OFF_PHI, &tm_phi, bar_phi, 0, jj * 128); }
            else tma_load_2d(sbase + (i > 4 ? 10 : 12) * SLOT - 4096 + i * 4096, &tm_wqB, bar_phi, (i > 4 ? 896 : 0) + jj * 128 + ((i - 1) >> 1) * 64, mm * 64 + (~i & 1) * 32);
          }
          __syncwarp();
          __nanosleep(PFGAP);
        }
      } else {
        if (XMMA && lane < 24) {
          const uint32_t one = (lane & 8) ? 0u : 0x3F80u << ((lane & 1) * 16), w = (lane >> 1) & 3;
          sts128(sbase + OFF_ID + lane * 16, w == 0 ? one : 0u, w == 1 ? one : 0u, w == 2 ? one : 0u, w == 3 ? one : 0u);
        }
#pragma unroll 1
        for (int b = 0; b < 2; b++) {
          float4* z = reinterpret_cast<float4*>(g_kv[b] + (jj * 4) * KVH + mm * (4 * KVH / 16)) + lane;
#pragma unroll
          for (int i = 0; i < 6; i++) z[i * 32] = make_float4(0.f, 0.f, 0.f, 0.f);
        }
#pragma unroll 1
        for (int i = 0; i < 16; i++) {
          const int b = i >> 2;
          const uint32_t v = (b == 0 ? O_BIT(0) : b == 1 ? X_BIT(0) : H_BIT(0)) + 1;
          uint4* p = b < 2 ? reinterpret_cast<uint4*>(g_obuf + (size_t)(b * S_LEN + mm * 128 + (i & 3) * 32 + (lane >> 3) * 8) * D_MODEL + jj * 128 + (b ? 0 : 64)) + (lane & 7)
                           : g_halo + (size_t)(mm * 8 + jj) * 512 + i * 32 + lane;
          *p = make_uint4(v, v, v, v);
        }
        fence_proxy_async_global();
      }
      __syncwarp();
      uint32_t chkp = 0;
#pragma unroll 1
      for (int lp = hw; lp < 8 * NLAYERS; lp++) {
        const int l = lp >> 3, tk = lp & 7, ph = tk ? 2 - hw : 0;
        const uint32_t par = l & 1;
        int lane; asm volatile("mov.u32 %0, %%laneid;" : "=r"(lane));
        if (tk == 5 || (hw && tk == 0)) {
          const uint32_t bit = ph ? O_BIT(l) : X_BIT(l - 1);
          uint32_t slots = ph ? (uint32_t)(WO_ASLOT(par) >> (ph * 32 - 28)) : 0x8769876u;
          const uint32_t a0 = sbase + (lane & 7) * 126 + lane * 4 + (lane & 1) * 14;
#pragma unroll 1
          for (int c = 0; c < 7; c++, slots >>= 4) {
            const uint32_t cb = bar_chk + 112 - hw * 112 + c * 8;
#pragma unroll 1
            for (int it = 0; it < (1 << 12); it++) {
              mbar_wait_sl(cb, (chkp >> c) & 1);
              chkp ^= 1u << c;
              if (el && c == 0) PROFT(ph == 1 ? 480 + l * 2 : 488 + l * 2 + (ph >> 1));
              uint32_t bad;
              asm volatile("{\n.reg .b32 w<16>;\n"
                           "ld.shared.u32 w0, [%1 + 0];\n"
                           "ld.shared.u32 w1, [%1 + 1024];\n"
                           "ld.shared.u32 w2, [%1 + 2048];\n"
                           "ld.shared.u32 w3, [%1 + 3072];\n"
                           "ld.shared.u32 w4, [%1 + 4096];\n"
                           "ld.shared.u32 w5, [%1 + 5120];\n"
                           "ld.shared.u32 w6, [%1 + 6144];\n"
                           "ld.shared.u32 w7, [%1 + 7168];\n"
                           "ld.shared.u32 w8, [%1 + 8192];\n"
                           "ld.shared.u32 w9, [%1 + 9216];\n"
                           "ld.shared.u32 w10, [%1 + 10240];\n"
                           "ld.shared.u32 w11, [%1 + 11264];\n"
                           "ld.shared.u32 w12, [%1 + 12288];\n"
                           "ld.shared.u32 w13, [%1 + 13312];\n"
                           "ld.shared.u32 w14, [%1 + 14336];\n"
                           "ld.shared.u32 w15, [%1 + 15360];\n"
                           "lop3.b32 w0, w0, w1, %2, 0x7E;\n"
                           "lop3.b32 w2, w2, w3, %2, 0x7E;\n"
                           "lop3.b32 w4, w4, w5, %2, 0x7E;\n"
                           "lop3.b32 w6, w6, w7, %2, 0x7E;\n"
                           "lop3.b32 w8, w8, w9, %2, 0x7E;\n"
                           "lop3.b32 w10, w10, w11, %2, 0x7E;\n"
                           "lop3.b32 w12, w12, w13, %2, 0x7E;\n"
                           "lop3.b32 w14, w14, w15, %2, 0x7E;\n"
                           "lop3.b32 w0, w0, w2, w4, 0xFE;\nlop3.b32 w6, w6, w8, w10, 0xFE;\nlop3.b32 w0, w0, w12, w14, 0xFE;\nlop3.b32 %0, w0, w6, 1, 0xA8;\n}\n"
                           : "=r"(bad) : "r"(a0 + (slots & 15) * SLOT), "r"(bit) : "memory");
              if (__all_sync(0xffffffffu, bad == 0)) break;
              if (el) {
                fence_proxy_async_smem();
                mbar_expect_tx(cb, SLOT);
                tma_load_2d(sbase + (slots & 15) * SLOT, &tm_o, cb, srcb(jj, c) * 128 + (ph >> 1) * 64, mm * 128 + (ph ? 0 : S_LEN));
                RETRY_COUNT();
              }
              __syncwarp();
            }
            if (el) { mbar_arrive_local(bar_full + (c + (ph ? 25 + ph * 8 : 4)) * 8); if (lp == PRL * 8 && c == 0) PROFT(477); }
            __syncwarp();
          }
        } else if (hw && (tk & 5) == 1) {
          {
            const int hp = tk >> 1;
            const uint4* src = reinterpret_cast<const uint4*>(g_colsum[par][jj * 64 + hp * 32 + lane]);
            uint32_t bad;
            int it = 0;
            float c[6];
            do {
              bad = 0;
#pragma unroll
              for (int p = 0; p < 3; p++) {
                const uint4 v = ld_ll(src + ((par && p < 2) ? (hp ? -32 : 512) + p * 32 : p * 512));
                bad |= (v.y ^ ep1) | (v.w ^ ep1);
                c[2 * p] = __uint_as_float(v.x) + __uint_as_float(v.z); c[2 * p + 1] = __uint_as_float(v.y) + __uint_as_float(v.w);
              }
              bad &= 3;
              if (bad) __nanosleep(300);
            } while (bad && ++it < (1 << 16));
#pragma unroll
            for (int p = 0; p < 6; p++) {
              uint32_t h, m, lo;
              split3(c[p], h, m, lo);
              sts128(sbase + OFF_LNB + hp * 4096 + (p >> 1) * 1024 + lane * 32 + (p & 1) * 16, h | (m << 16), h | (lo << 16), h | (m << 16), lo | (m << 16));
            }
            fence_proxy_async_smem();
            __syncwarp();
            if (el) { mbar_arrive_local(hp ? bar_stat2 : bar_stat); if (hp == 0) PROFT(324 + l * 16); }
            __syncwarp();
          }
        } else if (tk == 0) {
          mbar_wait_sl(bar_done + 24, par);
          const uint4* sp = reinterpret_cast<const uint4*>(g_stats + (size_t)(mm * 128) * 8) + lane;
#pragma unroll 1
          for (int hf = 0; hf < 4; hf++) {
            uint4 v[4];
            uint32_t bad;
            int it = 0;
            do {
              bad = 0;
#pragma unroll
              for (int i = 0; i < 4; i++) { v[i] = ld_ll(sp + (hf * 4 + i) * 32); bad |= (v[i].y ^ STAT_TAG(l)) | (v[i].w ^ STAT_TAG(l)); }
              bad &= 3;
              if (bad) __nanosleep(200);
            } while (bad && ++it < (1 << 16));
            __syncwarp();
            float mean = 0.f, m2 = 0.f;
#pragma unroll
            for (int i = 0; i < 4; i++) {
              float a = __uint_as_float(v[i].x) + __uint_as_float(v[i].z);
              a += __shfl_xor_sync(0xffffffffu, a, 1); a += __shfl_xor_sync(0xffffffffu, a, 2);
              a *= 0.125f;
              const float e0 = __uint_as_float(v[i].x) - a, e1 = __uint_as_float(v[i].z) - a;
              float q = fmaf(fmaf(e0, e0, e1 * e1), 128.f, __uint_as_float(v[i].y) + __uint_as_float(v[i].w));
              q += __shfl_xor_sync(0xffffffffu, q, 1); q += __shfl_xor_sync(0xffffffffu, q, 2);
              if ((lane & 3) == i) { mean = a; m2 = q; }
            }
            const uint32_t row = hf * 32 + (lane & 3) * 8 + (lane >> 2);
            uint32_t h, m, lo;
            split3(-0.5f * mean, h, m, lo);
            sts128(sbase + OFF_LNA + row * 16, h | (h << 16), m | (h << 16), lo | (m << 16), m | (lo << 16));
            sts32f(sbase + OFF_ST + row * 4, rsqrtf(m2 * (1.f / 1024.f) + 1e-5f));
          }
          fence_proxy_async_smem();
          __syncwarp();
          if (el) { mbar_arrive_local(bar_stat); PROFT(323 + l * 16); }
          __syncwarp();
#pragma unroll 1
          for (int i = 0; i < 8 - 4 * l; i++) {
            asm volatile("prefetch.global.L2 [%0];" :: "l"(i < 4 ? (l ? prm.wB_o : prm.wA_o) + (size_t)cta * 8192 + i * 2048 + lane * 64
                                                                 : prm.wB_qkv + (size_t)(cta * 8 + (i - 4) * 2 + (lane >> 4)) * 3072 + 2048 + (lane & 15) * 64));
            __nanosleep(PFGAP);
          }
        } else if (lp == 3) {
#pragma unroll 1
          for (int c = 0; c < (NLAYERS > 1 ? 8 : 0); c++) {
            if (!(c & 3)) asm volatile("bar.sync %0, 288;" :: "r"(BAR_WF + (c >> 2)) : "memory");
            if (el) {
              tma_store_2d(&tm_wf, sbase + 11 * SLOT + c * 4096, (c < 4 ? 1024 : -128) + jj * 128 + (c >> 1) * 64, mm * 64 + (c & 1) * 32);
              if ((c & 3) == 3) {
                asm volatile("cp.async.bulk.commit_group;\ncp.async.bulk.wait_group.read 0;" ::: "memory");
                mbar_arrive_local(bar_phi + (c >> 2) * 8);
              } else __nanosleep(WFGAP);
            }
            __syncwarp();
          }
          if (el) { bulk_commit_wait(); signal_release(&g_flags.wfready[jj].v); PROFT(335); }
          __syncwarp();
        } else if (tk == 2 || tk == 4) {
          if (par) continue;
          const int i = tk >> 2;
          mbar_wait_sl(bar_done + (i ? HW1 : (hw ? 19 : HW0)) * 8, 0);
          if (HDEL && i) __nanosleep(HDEL + hw * HDEL1);
          const uint4* src = g_halo + (size_t)(mm * 8 + jj - 8) * 512 + i * 256 + hw * 128 + lane;
          uint4 v[4];
          int it = 0;
          bool ok;
          do {
#pragma unroll
            for (int j = 0; j < 4; j++) v[j] = mm ? ld_b128(src + j * 32) : make_uint4(H_BIT(l), 0, 0, 0);
            ok = __all_sync(0xffffffffu, (((v[0].x ^ H_BIT(l)) | (v[1].x ^ H_BIT(l)) | (v[2].x ^ H_BIT(l)) | (v[3].x ^ H_BIT(l))) & 1) == 0);
            if (HSL && !ok) __nanosleep(HSL);
          } while (!ok && ++it < (1 << 16));
          if (lp + hw == 3 && NLAYERS > 1) mbar_wait_sl(bar_phi, 1);
#pragma unroll
          for (int j = 0; j < 4; j++) sts128(sbase + OFF_S + hw * SLOT + j * 512 + lane * 16, v[j].x, v[j].y, v[j].z, v[j].w);
          __syncwarp();
          if (el) { mbar_arrive_local(bar_halo + hw * 8); PROFT(331 + l * 16 + i * 2 + hw); }
          __syncwarp();
        } else if (tk == 6 && hw == 0 && l < NLAYERS - 1) {
          bar_sync<BAR_X1, 288>();
          if (el) {
            PROFT(328 + l * 16);
            mbar_wait_sl(bar_full + XD * 8, par ^ 1);
            tma_store_2d(&tm_o, sbase + 11 * SLOT, jj * 128 + 64, mm * 128 + S_LEN);
            bulk_commit_wait();
            signal_release(&g_flags.xready[l + 1][mm].v);
            PROFT(330 + l * 16);
          }
          __syncwarp();
        }
      }
    }
    cluster_sync();
  } else {
    asm volatile("setmaxnreg.inc.sync.aligned.u32 232;");
    const int wg = warp >> 2;
    const int r0 = warp * 16;
    const uint32_t pK = sbase + OFF_S, pV = sbase + OFF_S + SLOT;
#define PMASKS(on, bit) const uint32_t pm0 = ((on) && t == (g >> 1)), pbit = (bit)
#define PBIT0(w) (((w) & ~pm0) | (pbit & pm0))
#define PBIT1(w) (w)
#define LANE_CONSTS() \
    int lane; asm volatile("mov.u32 %0, %%laneid;" : "=r"(lane)); \
    const int g = lane >> 2, t = lane & 3; \
    const uint32_t srowoff = (r0 + (lane & 15)) * 128, lsw = (lane & 7) << 4, lhi = (lane >> 4) << 4, lsw2 = (lane & 6) << 3; \
    (void)g; (void)t; (void)srowoff; (void)lsw; (void)lhi; (void)lsw2;
    uint32_t stgp = 0, peer;
    asm volatile("mapa.shared::cluster.u32 %0, %1, %2;" : "=r"(peer) : "r"(sbase), "r"(rank ^ 1));
    peer -= sbase;
    const uint32_t dA0 = (((sbase & 0x3FFFF) + wg * 8192) >> 4) | 0x10000u, dB0 = ((sbase & 0x3FFFF) >> 4) | 0x2000000u;
    cluster_wait();
#define DESC(lo, hi) ((uint64_t)(uint32_t)(lo) | ((uint64_t)(hi) << 32))
#define STG_ARRIVE() { __syncwarp(); if (elect_one()) mbar_arrive_local(bar_stg); }
#define STG_WAIT() { mbar_wait(bar_stg, stgp); stgp ^= 1; }
#define PROFS() do {} while (0)
#define REL(addr) { if (elect_one()) { mbar_arrive_local(addr); asm volatile("mbarrier.arrive.shared::cluster.b64 _, [%0];" :: "r"((addr) + peer) : "memory"); } }
#define QSTEP(ACC, DA, SC, PRE) { \
      const uint32_t da = (DA), db = dB0 + (ub & 0x18) * (QST >> 7); \
      mbar_wait(ub, par); \
      PRE; \
      wgmma_fence(); \
      wgmma4_n192<SC>(ACC, da, db); \
      wgmma_commit(); PROFS(); }
#define QREL() { wgmma_wait<1>(); REL(ub + 376); ub += 8; }
#define RA_CUR (dA0 + (OFF_RA >> 4) + (ub & 0x18) * (SLOT >> 7))
#define PUMP1() { QSTEP(S1, RA_CUR, 1, {}); QREL(); }
#define PUMP0() { PUMP1(); SCHED_FENCE(); }
#define PUMP() if (h == 0) PUMP1()
#define WSTEP() { \
      const uint32_t s4 = (ub - bar_full - 256) >> 1; \
      const uint32_t da = dA0 + (((uint32_t)(WO_ASLOT(par) >> s4) & 15) << 10), db = dB0 + (((uint32_t)(WO_BSLOT >> s4) & 15) << 10); \
      mbar_wait(ub, par); \
      wgmma_fence(); \
      wgmma4_n128<1>(S1, da, db); \
      wgmma_commit(); PROFS(); \
      wgmma_wait<1>(); \
      if (s4) REL(ub + 376); \
      ub += 8; }
#define PUMPS(n) { _Pragma("unroll 1") for (int i_ = 0; i_ < (n); i_++) PUMP1(); }
#define SITE(n) { if ((BMASK >> (n)) & 1) PUMP1(); SCHED_FENCE(); }
#define LNSTEP(ACC, hh) { wgmma_fence(); wgmma_n192<1, 0>(ACC, make_desc(sbase + OFF_LNA + wg * 1024, 0, 128) ^ (1ull << 62), make_desc(sbase + OFF_LNB + (hh) * 4096, 0, 128) ^ (1ull << 62)); }
#define WARP_STORE(tm, tile, col, row) { fence_proxy_async_smem(); __syncwarp(); \
      if (elect_one()) { tma_store_2d(tm, (tile) + r0 * 128, col, (row) + r0); asm volatile("cp.async.bulk.commit_group;" ::: "memory"); } __syncwarp(); }
#define PUBLISH_O() WARP_STORE(&tm_os, pO, jj * 128 + h * 64, mm * 128)
#define TILE_CONSTS(base, on, bit) \
      uint32_t ta[5]; \
      { PMASKS(on, bit); (void)pbit; ta[4] = pm0; } \
      _Pragma("unroll") for (int j = 0; j < 4; j++) ta[j] = (base) + srowoff + ((((uint32_t)j << 5) + lhi) ^ lsw); \
      PINU(ta, 5); SCHED_FENCE(); \
      const uint32_t pm0 = ta[4], pbit = (bit)
#define X_OUT(pc, W) { \
      _Pragma("unroll") for (int j = 0; j < 4; j++) \
        stsm_x4(ta[j] + (pc) * SLOT, \
                PBIT0(pack_bf16((W)[j * 8 + 0], (W)[j * 8 + 1])), PBIT0(pack_bf16((W)[j * 8 + 2], (W)[j * 8 + 3])), \
                PBIT1(pack_bf16((W)[j * 8 + 4], (W)[j * 8 + 5])), PBIT1(pack_bf16((W)[j * 8 + 6], (W)[j * 8 + 7]))); }
#define REST_P1(SKEW) { \
      mbar_wait(bar_stat2, par); \
      LNSTEP(S1, 1); \
      _Pragma("unroll 1") while (ub < bar_full + 256) { \
        if (ub == bar_full + 256 - 8 * (SKEW) && wg == 0) bar_sync<BAR_SKEW, 256>(); \
        QSTEP(S1, RA_CUR, 1, {}); \
        if (ub == bar_full + 248 && wg == 1) bar_arrive<BAR_SKEW, 256>(); \
        QREL(); \
      } \
      mbar_wait(bar_done + (31 - (SKEW)) * 8, par);        \
      wgmma_wait<0>(); \
      ACC_FENCE(S1, 96); \
      REL(bar_done + 31 * 8); \
      PROF(13); }
#define FOLD(tile, rd) { \
          LANE_CONSTS(); \
          float d[32]; \
          ACC_DEF(d, 32); \
          mbar_wait(bar_phi, 0); \
          wgmma_fence(); \
          _Pragma("unroll") for (int i = 0; i < 2; i++) { \
            const uint64_t da = make_desc((tile) + wg * 8192 + i * 64, 16, 1024); \
            const uint64_t db = make_desc(sbase + OFF_PHI + wg * 4096 + i * 2048, 16, 512) ^ (3ull << 62); \
            wgmma_n32<0>(d + i * 16, da, db); wgmma_n32<1>(d + i * 16, da + 2, db + 64); \
          } \
          wgmma_commit(); \
          PUMP0(); \
          ACC_FENCE(d, 32); \
          bar_wg(wg); \
          _Pragma("unroll") for (int i = 0; i < 4; i++) { \
            const float* x = d + (i & 1) * 8 + (i >> 1) * 2; \
            if (rd) sts128((tile) + wg * 8192 + ((warp & 3) * 16 + (i >> 1) * 8 + g) * 128 + (((2 * t + (i & 1)) ^ g) << 4), \
                           pack_bf16(x[0], x[1]), pack_bf16(x[4], x[5]), pack_bf16(x[16], x[17]), pack_bf16(x[20], x[21])); \
            else stsm_x4((tile) + srowoff + ((((uint32_t)i << 5) + lhi) ^ lsw), pack_bf16(d[i * 8], d[i * 8 + 1]), pack_bf16(d[i * 8 + 2], d[i * 8 + 3]), \
                         pack_bf16(d[i * 8 + 4], d[i * 8 + 5]), pack_bf16(d[i * 8 + 6], d[i * 8 + 7])); \
          } \
          }
#define LOAD_X0(base) \
      _Pragma("unroll") for (int j = 0; j < 8; j++) { \
        uint32_t x0, x1, x2, x3; \
        ldsm_x4((base) + (j >> 2) * SLOT + srowoff + ((((uint32_t)(j & 3) << 5) + lhi) ^ lsw), x0, x1, x2, x3); \
        S1[j * 8 + 0] = bf_lo(x0); S1[j * 8 + 1] = bf_hi(x0); S1[j * 8 + 2] = bf_lo(x1); S1[j * 8 + 3] = bf_hi(x1); \
        S1[j * 8 + 4] = bf_lo(x2); S1[j * 8 + 5] = bf_hi(x2); S1[j * 8 + 6] = bf_lo(x3); S1[j * 8 + 7] = bf_hi(x3); \
      }
#define XM_ISSUE(keep) { mbar_wait(bar_xr, par); wgmma_fence(); \
      wgmma_copy(T_, dA0 + (OFF_RA >> 4), ((keep) ? make_desc(sbase + OFF_ID + 128, 0, 0) : make_desc(sbase + OFF_ID, 128, 128)) ^ (1ull << 62), keep); }
#define COPYN(d, s, n) _Pragma("unroll") for (int i_ = 0; i_ < (n); i_++) { uint32_t c_; asm volatile("mov.b32 %0, %1;" : "=r"(c_) : "f"((s)[i_])); (d)[i_] = __uint_as_float(c_); }
#define COPY64(d, s) COPYN(d, s, 64)
#define XM_DONE(c) { ACC_FENCE(T_, 64); COPY64(S1, T_); ACC_FENCE(S1, 64); \
      __syncwarp(); if ((c) && elect_one()) mbar_arrive_local(bar_lx); }
#define LOAD_X() { float T_[64]; ACC_DEF(T_, 64); wgmma_wait<0>(); XM_ISSUE(0); wgmma_commit(); wgmma_wait<0>(); XM_DONE(true); }

    float S0[96], S1[96];
#define FIRST_STEP(l_) { const int ln_ = (l_), l = ln_; const uint32_t par = l & 1, ub = bar_full; ACC_DEF(S0, 96); QSTEP(S0, dA0 + (OFF_S >> 4), 0, {}); }
    FIRST_STEP(0);
    LOAD_EPOCH();
#pragma unroll 1
    for (int l = 0;; l++) {
      const uint32_t par = l & 1;
      uint32_t ub = bar_full + 8;
      PROF(1);
      {
        LANE_CONSTS();
        uint32_t ta[4];
#pragma unroll
        for (int j = 0; j < 4; j++) ta[j] = pK + srowoff + ((((uint32_t)j << 5) + lhi) ^ lsw);
        float p0, p1, a0 = 0.f, a1 = 0.f, q0 = 0.f, q1 = 0.f;
#define STATS(j0, j1) _Pragma("unroll") for (int j = (j0); j < (j1); j++) { \
          uint32_t x[4]; \
          ldsm_x4(ta[j & 3] + (j >> 2) * SLOT, x[0], x[1], x[2], x[3]); \
          if (j == 0) { p0 = __shfl_sync(0xffffffffu, bf_lo(x[0]), lane & 28); p1 = __shfl_sync(0xffffffffu, bf_lo(x[1]), lane & 28); } \
          _Pragma("unroll") for (int i = 0; i < 4; i += 2) { \
            const float d0 = bf_lo(x[i]) - p0, d1 = bf_hi(x[i]) - p0, d2 = bf_lo(x[i + 1]) - p1, d3 = bf_hi(x[i + 1]) - p1; \
            a0 += d0 + d1; a1 += d2 + d3; \
            q0 = fmaf(d1, d1, fmaf(d0, d0, q0)); q1 = fmaf(d3, d3, fmaf(d2, d2, q1)); } } \
          asm volatile("" : "+f"(a0), "+f"(a1), "+f"(q0), "+f"(q1), "+f"(p0), "+f"(p1)); SCHED_FENCE()
        if (SB0) { STATS(0, SB0); }
        if (!(NOBW >> 0 & 1)) bar_wg(wg);
        QSTEP(S0, dA0 + ((OFF_S + SLOT) >> 4), 1, {});
        QREL();
        SCHED_FENCE();
        STATS(SB0, SB1);
        ACC_DEF(S1, 96);
        QSTEP(S1, dA0 + (OFF_S >> 4), 0, {});
        QREL();
        SCHED_FENCE();
        STATS(SB1, SB2);
        QSTEP(S1, dA0 + ((OFF_S + SLOT) >> 4), 1, {});
        QREL();
        SCHED_FENCE();
        STATS(SB2, 8);
#pragma unroll
        for (int o = 1; o <= 2; o <<= 1) {
          a0 += __shfl_xor_sync(0xffffffffu, a0, o); a1 += __shfl_xor_sync(0xffffffffu, a1, o);
          q0 += __shfl_xor_sync(0xffffffffu, q0, o); q1 += __shfl_xor_sync(0xffffffffu, q1, o);
        }
        if (t == 1) { a0 = a1; q0 = q1; p0 = p1; }
        if (t < 2) st_b64(g_stats + (size_t)(mm * 128 + r0 + g + t * 8) * 8 + jj, __float_as_uint(fmaf(a0, 1.f / 128.f, p0)),
                          (__float_as_uint(fmaxf(fmaf(a0 * (-1.f / 128.f), a0, q0), 0.f)) & ~3u) | STAT_TAG(l));
        if (l) { asm volatile("cp.async.bulk.wait_group 0;" ::: "memory"); bar_arrive<BAR_X1, 288>(); }
#pragma unroll 1
        for (int i = 0; i < 14; i++) {
          QSTEP(S0, RA_CUR, 1, {});
          if (i == 0) PROF(2);
          QREL();
        }
      }
      LANE_CONSTS();
      mbar_wait(bar_stat, par);
      LNSTEP(S0, 0);
      wgmma_commit();
      const float rs0 = lds32f(sbase + OFF_ST + (r0 + g) * 4), rs1 = lds32f(sbase + OFF_ST + (r0 + g + 8) * 4);
      PUMP0();
      ACC_FENCE(S0, 96);
      PROF(3);
      if (!par) {
        constexpr uint32_t par = 0;
        uint32_t qa[16];
        uint32_t kf[32], vf[32];
#define DRAIN_A(ACC, hp, PMP) { \
          LANE_CONSTS(); \
          FRAG(kf + 16, ACC + 32, 0, (hp) * 2); \
          PMP; \
          FRAG(vf + 16, ACC + 64, 1, (hp) * 2 + 1); \
          _Pragma("unroll") for (int i_ = 0; i_ < 16; i_++) qa[i_] = pack_bf16(ACC[2 * i_], ACC[2 * i_ + 1]); \
          PINU(qa, 16); }
        DRAIN_A(S0, 0, PUMP0());
        if (l == 0 && NLAYERS > 1) {
#pragma unroll 1
          for (int rd = 1; rd >= 0; rd--) {
            FOLD(sbase + (12 - rd) * SLOT, rd);
            fence_proxy_async_smem();
            asm volatile("bar.arrive %0, 288;" :: "r"(BAR_WF + 1 - rd) : "memory");
          }
        }
        PUMPS(FPUMP);
        if (l == 0 && NLAYERS > 1) mbar_wait(bar_phi, 1);
#pragma unroll 1
        for (int h = 0; h < 2; h++) {
          const uint32_t pO = sbase + (h ? 3 : 12) * SLOT;
          PROFH(4, 16);
          LANE_CONSTS();
          if (XA && h) {
            float T_[64];
            ACC_DEF(T_, 64);
            if (XA == 2) { FRAG_PUT(kf + 16, 10); }
            XM_ISSUE(0); wgmma_commit();
            SCHED_FENCE();
            if (XA == 1) { FRAG_PUT(kf + 16, 10); }
            FRAG_PUT(vf + 16, 11);
            STG_ARRIVE();
            SCHED_FENCE();
            wgmma_wait<0>(); XM_DONE(true);
          } else {
            FRAG_PUT(kf + 16, 10); FRAG_PUT(vf + 16, 11);
            STG_ARRIVE();
          }
          if (h) { if (!XA && AW0 < 4) LOAD_X(); if (AW0 == 1) WSTEP(); } else PUMPS(HPUMP2);
          const bool e = g & 1, hb = (2 * t + (g & 1)) <= g;
          uint32_t sel[3] = {e ? 0x1044u : 0x4410u, hb ? 0x4444u : (e ? 0x3244u : 0x4432u), hb ? (e ? 0x3244u : 0x4432u) : 0x4444u};
          PINU(sel, 3);
          TILE_CONSTS(pO, true, O_BIT(l));
          const uint32_t selA = sel[0], selL = sel[1], selH = sel[2];
          STG_WAIT();
          if (warp == 0) mbar_wait(bar_halo, h);
          FRAG_GET(kf, 10);
          PROFH(5, 17);
          float s[2][4][4];
#pragma unroll
          for (int ks = 0; ks < 2; ks++)
#pragma unroll
            for (int i = 0; i < 8; i++) {
              const int hh = (i >> 1) & 1, jb = (i & 1) + (~i >> 1 & 2);
              const uint32_t* b = kf + (jb >> 1) * 16 + hh * 8 + ks * 4 + (jb & 1) * 2;
              if (ks) mma_bf16(s[hh][jb], qa[hh * 8 + 4], qa[hh * 8 + 5], qa[hh * 8 + 6], qa[hh * 8 + 7], b[0], b[1]);
              else mma_bf16_z(s[hh][jb], qa[hh * 8], qa[hh * 8 + 1], qa[hh * 8 + 2], qa[hh * 8 + 3], b[0], b[1]);
            }
          if (h == 0) PUMP1() else if (AW0 == 2 || AW0 == 4) { if (AW0 == 4) LOAD_X(); WSTEP(); }
          PROFH(6, 18);
          float va[2][2], vb[2][2], mx[2][2];
#pragma unroll
          for (int hh = 0; hh < 2; hh++) {
            va[hh][0] = e ? s[hh][1][1] : s[hh][1][0];
            vb[hh][0] = hb ? (e ? s[hh][2][1] : s[hh][2][0]) : (e ? s[hh][0][1] : s[hh][0][0]);
            va[hh][1] = e ? s[hh][2][3] : s[hh][2][2];
            vb[hh][1] = hb ? (e ? s[hh][3][3] : s[hh][3][2]) : (e ? s[hh][1][3] : s[hh][1][2]);
          }
          if (warp == 0 && mm == 0) {
#pragma unroll
            for (int hh = 0; hh < 2; hh++) { va[hh][0] = -INFINITY; if (!hb) { vb[hh][0] = -INFINITY; vb[hh][1] = -INFINITY; } }
          }
#pragma unroll
          for (int i = 0; i < 4; i++) mx[i >> 1][i & 1] = fmaxf(va[i >> 1][i & 1], vb[i >> 1][i & 1]);
#pragma unroll
          for (int o = 1; o <= 2; o <<= 1)
#pragma unroll
            for (int i = 0; i < 4; i++) mx[i >> 1][i & 1] = fmaxf(mx[i >> 1][i & 1], __shfl_xor_sync(0xffffffffu, mx[i >> 1][i & 1], o));
          const float sc0 = rs0 * (0.17677669529663687f * LOG2E), sc1 = rs1 * (0.17677669529663687f * LOG2E);
#pragma unroll
          for (int i = 0; i < 4; i++) {
            const float sc = (i & 1) ? sc1 : sc0, m = mx[i >> 1][i & 1];
            va[i >> 1][i & 1] = ex2((va[i >> 1][i & 1] - m) * sc); vb[i >> 1][i & 1] = ex2((vb[i >> 1][i & 1] - m) * sc);
            mx[i >> 1][i & 1] = va[i >> 1][i & 1] + vb[i >> 1][i & 1];
          }
          if (h == 0 && ASITE) { PIN(&va[0][0], 4); PIN(&vb[0][0], 4); PIN(&mx[0][0], 4); PUMP1(); } else if (AW0 == 3) WSTEP();
          if (warp == 0) mbar_wait(bar_halo + 8, h);
          FRAG_GET(vf, 11);
#pragma unroll
          for (int o = 1; o <= 2; o <<= 1)
#pragma unroll
            for (int i = 0; i < 4; i++) mx[i >> 1][i & 1] += __shfl_xor_sync(0xffffffffu, mx[i >> 1][i & 1], o);
          float o[2][4][4];
          uint32_t pa[2][8];
#pragma unroll
          for (int hh = 0; hh < 2; hh++) {
            const float i0 = rcp_fast(mx[hh][0]), i1 = rcp_fast(mx[hh][1]);
            const uint32_t w0 = pack_bf16(va[hh][0] * i0, vb[hh][0] * i0), w1 = pack_bf16(va[hh][1] * i1, vb[hh][1] * i1);
            pa[hh][0] = __byte_perm(w0, 0, selL); pa[hh][2] = __byte_perm(w0, 0, selA); pa[hh][3] = __byte_perm(w1, 0, selL);
            pa[hh][4] = __byte_perm(w0, 0, selH); pa[hh][5] = __byte_perm(w1, 0, selA); pa[hh][7] = __byte_perm(w1, 0, selH);
            pa[hh][1] = pa[hh][0] & pa[hh][4]; pa[hh][6] = pa[hh][3] & pa[hh][7];
          }
          PROFH(7, 19);
#pragma unroll
          for (int i = 0; i < 8; i++) mma_bf16_z(o[i >> 2][i & 3], pa[i >> 2][4], pa[i >> 2][5], pa[i >> 2][6], pa[i >> 2][7], vf[16 + 2 * i], vf[17 + 2 * i]);
#pragma unroll
          for (int i = 0; i < 8; i++) mma_bf16(o[i >> 2][i & 3], pa[i >> 2][0], pa[i >> 2][1], pa[i >> 2][2], pa[i >> 2][3], vf[2 * i], vf[2 * i + 1]);
          if (h == 0) PUMP1() else mbar_wait(bar_done + 30 * 8, par);
          if (NLAYERS > 1) mbar_wait(bar_phi + 8, 0);
#pragma unroll
          for (int i = 0; i < 4; i++) {
            const int hh = i >> 1, dp = i & 1;
            stsm_x4(ta[i],
                    PBIT0(pack_bf16(o[hh][dp * 2][0], o[hh][dp * 2][1])), PBIT0(pack_bf16(o[hh][dp * 2][2], o[hh][dp * 2][3])),
                    PBIT1(pack_bf16(o[hh][dp * 2 + 1][0], o[hh][dp * 2 + 1][1])), PBIT1(pack_bf16(o[hh][dp * 2 + 1][2], o[hh][dp * 2 + 1][3])));
          }
          PUBLISH_O();
          PROFH(11, 23);
          if (h) break;
          REST_P1(ASKEW);
          asm volatile("cp.async.bulk.wait_group.read 0;" ::: "memory");
          DRAIN_A(S1, 1, {});
        }
      } else {
        constexpr uint32_t par = 1;
        float st[32];
        const float c0 = rs0 * LOG2E, c1 = rs1 * LOG2E;
        { V_ADDR(pV); STAGE_V(S0 + 64); }
        if (warp < 2) sts128(sbase + OFF_ONES + warp * 512 + lane * 16, 0x3F803F80u, 0x3F803F80u, 0x3F803F80u, 0x3F803F80u);
        scale32(st, S0, c0, c1);
        PIN(st, 32);
#define PHI_PIECE(c) { \
          e_[2 * (c)] = ex2(st[2 * (c)]); e_[2 * (c) + 1] = ex2(st[2 * (c) + 1]); \
          _Pragma("unroll") for (int k_ = 4 * (c); k_ < 4 * (c) + 4; k_++) m_[(c) >> 1] = (k_ & 7) ? fmaf(st[k_], st[k_], m_[(c) >> 1]) : st[k_] * st[k_]; \
          asm volatile("" : "+f"(e_[2 * (c)]), "+f"(e_[2 * (c) + 1]), "+f"(m_[(c) >> 1])); SCHED_FENCE(); }
#define PHI_FIN() { \
          big = __any_sync(0xffffffffu, !(fmaxf(fmaxf(m_[0], m_[1]), fmaxf(m_[2], m_[3])) < BIGLIM)); \
          if (__builtin_expect(big, 0)) { COPYN(e_, st, 16); } \
          _Pragma("unroll") for (int k_ = 0; k_ < 16; k_++) st[k_] = e_[k_]; \
          PIN(st, 16); }
#define KV_MMA(vs, IL) { \
          const uint32_t dp = dA0 + 12 * 1024 - wg * 2560, dv = dA0 + (vs) * 1024 + ((OFF_ONES - (vs) * SLOT - 16) << 12) - wg * (512 << 16); \
          STG_WAIT(); \
          wgmma_fence(); \
          _Pragma("unroll") for (int ks = 0; ks < 8; ks++) { \
            const uint64_t a = DESC(dp + ks * 128, 0x40000040), b = DESC(dv + ks * (64 - (64 << 16)), 0x80000020); \
            if ((IL) && ks) wgmma_fence(); \
            if (ks == 0) wgmma_n40<0, 1>(kv, a, b); else wgmma_n40<1, 1>(kv, a, b); \
            if (ks == 7) wgmma_commit(); \
            if (IL) PHI_PIECE(ks); } }
#define KV_RED(hp) { \
          float* kvg = g_kv[l >> 1] + (jj * 4 + (hp) * 2) * KVH + warp * 768 + lane * 4; \
          _Pragma("unroll") for (int i = 0; i < 5; i++) red_v4(kvg + i * 128, kv[i * 3], kv[i * 3 + 1], kv[i * 3 + 2], 1.f); \
          red_v4(kvg + 640, kv[15], kv[16], kv[18], 1.f); }
#define KV_RED1(i) if (h) red_v4(g_kv[l >> 1] + (jj * 4) * KVH + warp * 768 + lane * 4 + (i) * 128, S0[32 + (i) * 3], S0[33 + (i) * 3], S0[34 + (i) * 3], 1.f)
#define KV_REDS(n) { if (PAIR & 1) { if (h && (n) == PPOS0) KV_RECV(S0 + 32, 0); } else _Pragma("unroll") for (int i_ = 0; i_ < 6; i_++) if (((RPACE >> (4 * i_)) & 15) == (n)) KV_RED1(i_); }
#define KV_SEND(kp) { \
          float sd[9]; \
          kv[17] = kv[18]; \
          _Pragma("unroll") for (int i = 0; i < 9; i++) { (kp)[i] = rank ? kv[9 + i] : kv[i]; sd[i] = rank ? kv[i] : kv[9 + i]; } \
          const uint32_t ra = sbase + peer + (warp * 32 + lane) * 4, rb = bar_kx + peer; \
          if (elect_one()) mbar_expect_tx(bar_kx, 1152); \
          _Pragma("unroll") for (int i = 0; i < 2; i++) \
            asm volatile("st.async.weak.shared::cluster.mbarrier::complete_tx::bytes.v4.f32 [%0], {%1, %2, %3, %4}, [%5];" \
                         :: "r"(ra + (warp * 32 + lane) * 12 + OFF_PHI + i * 4096), "f"(sd[4 * i]), "f"(sd[4 * i + 1]), "f"(sd[4 * i + 2]), "f"(sd[4 * i + 3]), "r"(rb) : "memory"); \
          asm volatile("st.async.weak.shared::cluster.mbarrier::complete_tx::bytes.f32 [%0], %1, [%2];" :: "r"(ra + OFF_LNB), "f"(sd[8]), "r"(rb) : "memory"); }
#define KV_RECV(kp, hp) { \
          float r_[9]; \
          float* kvg = g_kv[l >> 1] + (jj * 4 + (hp) * 2) * KVH + warp * 768 + rank * 384 + lane * 4; \
          mbar_wait(bar_kx, PAIR == 3 ? (hp) : (l >> 1)); \
          _Pragma("unroll") for (int i = 0; i < 2; i++) \
            asm volatile("ld.shared.v4.f32 {%0, %1, %2, %3}, [%4];" : "=f"(r_[4 * i]), "=f"(r_[4 * i + 1]), "=f"(r_[4 * i + 2]), "=f"(r_[4 * i + 3]) \
                         : "r"(sbase + OFF_PHI + i * 4096 + (warp * 32 + lane) * 16) : "memory"); \
          r_[8] = lds32f(sbase + OFF_LNB + (warp * 32 + lane) * 4); \
          _Pragma("unroll") for (int i = 0; i < 3; i++) red_v4(kvg + i * 128, (kp)[3 * i] + r_[3 * i], (kp)[3 * i + 1] + r_[3 * i + 1], (kp)[3 * i + 2] + r_[3 * i + 2], 2.f); }
#define KV_LOAD(hp) { \
          const uint4* kvg = reinterpret_cast<const uint4*>(g_kv[l >> 1] + (jj * 4 + (hp) * 2) * KVH) + warp * 192 + lane; \
          _Pragma("unroll") for (int i = 0; i < 6; i++) v[i] = ld_b128(kvg + i * 32); }
#define KVV(i) __uint_as_float((i) % 3 == 0 ? v[(i) / 3].x : ((i) % 3 == 1 ? v[(i) / 3].y : v[(i) / 3].z))
#define KV_TILE(hp) { \
          _Pragma("unroll 1") for (int it = 0; it < (1 << 16); it++) { \
            if (__all_sync(0xffffffffu, (v[0].w & v[1].w & v[2].w & v[3].w & v[4].w & v[5].w) == 0x41800000u)) break; \
            RETRY_COUNT(); \
            KV_LOAD(hp); \
          } \
          if (hp) PROF(26); else PROF(25); \
          const uint32_t e = lane & 7, jt = ((lane >> 1) & 4) + (e >> 1); \
          const uint32_t row = ((((warp >> 1) ^ wg) & 1) << 5) + ((jt & 1) << 4) + ((warp & 1) << 3) + (jt & 6) + (e & 1); \
          const uint32_t kd = pV + wg * 8192 + row * 128, ksw = (row & 7) << 4; \
          _Pragma("unroll") for (int i = 0; i < 2; i++) \
            stsm_x4(kd + ((i * 32 + lhi) ^ ksw), pack_bf16(KVV(i * 8), KVV(i * 8 + 1)), pack_bf16(KVV(i * 8 + 2), KVV(i * 8 + 3)), \
                    pack_bf16(KVV(i * 8 + 4), KVV(i * 8 + 5)), pack_bf16(KVV(i * 8 + 6), KVV(i * 8 + 7))); \
          stsm_x4(kd + ((64u + lhi) ^ ksw), pack_bf16(KVV(16), 1.f), pack_bf16(KVV(17), 1.f), 0u, 0u); }
#pragma unroll 1
        for (int h = 0; h < 2; h++) {
          PROFH(4, 6);
          SITE(0);
          LANE_CONSTS();
          const uint32_t dsw = (uint32_t)(g ^ (2 * t)) << 4, dst = ((t & 2) ? pK : sbase + 12 * SLOT) + (r0 + g) * 128;
          float e[16], f[16];
          KV_REDS(1);
          float sa = exps16_<0>(e, st);
          exps16_fix<0>(e, st, sa);
          asm volatile("" : "+f"(sa)); PIN(e, 16); SITE(1);
          if (h) STG_WAIT();
          KV_REDS(2);
          store16(e, sa, dst, dsw, 4);
          float sb = exps16_<1>(f, st);
          exps16_fix<1>(f, st, sb);
          asm volatile("" : "+f"(sb)); PIN(f, 16); SITE(2);
          KV_REDS(3);
          store16(f, sb, dst, dsw, 0);
          float sc = exps16_<0>(e, st + 2);
          exps16_fix<0>(e, st + 2, sc);
          asm volatile("" : "+f"(sc)); PIN(e, 16); SITE(3);
          KV_REDS(4);
          store16(e, sc, dst + 1024, dsw, 4);
          float sd = exps16_<1>(f, st + 2);
          exps16_fix<1>(f, st + 2, sd);
          asm volatile("" : "+f"(sd)); PIN(f, 16); SITE(4);
          store16(f, sd, dst + 1024, dsw, 0);
          PROFH(5, 7);
          if (h) break;
          {
            float kv[20];
            ACC_DEF(kv, 20);
            fence_proxy_async_smem();
            STG_ARRIVE();
            float e_[16], m_[4];
            KV_MMA(11, 0);
            PUMP0();
            ACC_FENCE(kv, 20);
            STG_ARRIVE();
            scale32(st, S0 + 32, c0, c1);
            PIN(st, 32);
            if (PAIR & 1) { KV_SEND(S0 + 32); PIN(S0 + 32, 9); }
            else {
              kv[17] = kv[18];
              COPYN(S0 + 32, kv, 18);
              const int h = 1;
              KV_REDS(0);
            }
          }
        }
        bool big;
        uint4 v[6];
        {
          float kv[20];
          if (KT0) { LANE_CONSTS(); KV_LOAD(0); }
          mbar_wait(bar_stat2, par);
          LNSTEP(S1, 1);
          ub = bar_full + 240;
          PUMP1();
          if (wg == 0) bar_sync<BAR_SKEW, 256>();
          QSTEP(S1, RA_CUR, 1, {});
          if (wg == 1) bar_arrive<BAR_SKEW, 256>();
          QREL();
          if (KT0 == 2) { LANE_CONSTS(); KV_TILE(0); }
          LANE_CONSTS();
          V_ADDR(sbase + 3 * SLOT);
          PINU(va_, 2);
          mbar_wait(bar_done + 30 * 8, par);
          wgmma_wait<0>();
          ACC_FENCE(S1, 96);
          if (!(RLATE & 2)) REL(bar_done + 31 * 8);
          PROF(13);
          STAGE_V(S1 + 64);
          fence_proxy_async_smem();
          STG_ARRIVE();
          if (RLATE & 2) REL(bar_done + 31 * 8);
          scale32(st, S1, c0, c1);
          PIN(st, 32);
          PROF(16);
          ACC_DEF(kv, 20);
          float e_[16], m_[4];
          KV_MMA(3, ILV & 1);
          SCHED_FENCE();
          PROF(14);
          if (ILV & 1) PHI_FIN() else if (!SEARLY) { big = any_big(st); phiq_a(st, big); PIN(st, 16); }
          if (SEARLY == 2) big = any_big(st);
          SCHED_FENCE();
          PROF(15);
          wgmma_wait<0>();
          ACC_FENCE(kv, 20);
          PROF(12);
          if (PAIR & 2) { float kp[9]; KV_SEND(kp); _Pragma("unroll") for (int i = 0; i < 3; i++) v[i] = make_uint4(__float_as_uint(kp[3 * i]), __float_as_uint(kp[3 * i + 1]), __float_as_uint(kp[3 * i + 2]), 0u); }
          else KV_RED(1);
          if (SEARLY) { SCHED_FENCE(); if (SEARLY == 1) big = any_big(st); phiq_a(st, big); PIN(st, 16); SCHED_FENCE(); }
          PROF(17);
        }
#pragma unroll 1
        for (int h = 0; h < 2; h++) {
          const uint32_t pO = sbase + (h ? 3 : 8) * SLOT;
          LANE_CONSTS();
          uint32_t fq[32];
#define KV_RECV1(pos) if ((PAIR & 2) && PPOS == (pos) && h == 0) { float kp[9]; _Pragma("unroll") for (int i = 0; i < 9; i++) kp[i] = KVV(i); KV_RECV(kp, 1); SCHED_FENCE(); }
          KV_RECV1(0);
          PROFH(18, 32);
          SCHED_FENCE();
          if (h) {
            asm volatile("cp.async.bulk.wait_group.read 0;" ::: "memory");
            mbar_wait(bar_lx, par);
            PROF(30);
          }
          if (h || KT0 < 2) {
            KV_TILE(h);
            fence_proxy_async_smem();
            STG_ARRIVE();
          }
          SCHED_FENCE();
          phiq_b<1>(fq, st, big); PINU(fq, 16); PIN(st + 16, 16);
          PROFH(8, 9);
          KV_RECV1(1);
          if (h || KT0 < 2) STG_WAIT();
          wgmma_wait<0>();
          ACC_FENCE(S1, 64);
          float T_[64];
          if (XB == 3) { COPY64(T_, S1); }
          PROFH(19, 33);
          float o[4][20];
#define O_MMA(hh) { \
            const uint64_t db = make_desc(pV + (hh) * 8192, 16, 1024); \
            ACC_DEF(o[(hh) * 2], 20); ACC_DEF(o[(hh) * 2 + 1], 20); \
            wgmma_fence(); \
            wgmma_n40_rs<0>(o[(hh) * 2], fq + (hh) * 16, db + 256); wgmma_n40_rs<0>(o[(hh) * 2 + 1], fq + (hh) * 16 + 8, db); \
            wgmma_n40_rs<1>(o[(hh) * 2], fq + (hh) * 16 + 4, db + 384); wgmma_n40_rs<1>(o[(hh) * 2 + 1], fq + (hh) * 16 + 12, db + 128); \
            wgmma_commit(); }
          O_MMA(0);
          SCHED_FENCE();
          KV_RECV1(2);
          phiq_b<0>(fq + 16, st + 16, big); PINU(fq + 16, 16);
          KV_RECV1(3);
          PROFH(10, 21);
          SCHED_FENCE();
          PMASKS(true, O_BIT(l));
#pragma unroll
          for (int hh = 0; hh < 2; hh++) {
            if (hh && !OW) O_MMA(1);
            if (XB == 3 && hh) { scale32(st, T_ + 32, c0, c1); PIN(st, 32); XM_ISSUE(h); wgmma_commit(); wgmma_wait<1>(); } else
            wgmma_wait<0>();
            ACC_FENCE(o[hh * 2], 20); ACC_FENCE(o[hh * 2 + 1], 20);
            if (!hh && OW) { O_MMA(1); SCHED_FENCE(); }
            if (hh) PROFH(22, 24);
            const float* x = o[hh * 2];
            const float* y = o[hh * 2 + 1];
            const float sx0 = x[17] * 0x1p-40f, sy0 = y[17] * 0x1p-40f, sx1 = x[19] * 0x1p-40f, sy1 = y[19] * 0x1p-40f;
            const float i0 = rcp_fast(fmaf(fmaf(x[17], 1e-6f, x[16]), sy0, y[16] * sx0)), i1 = rcp_fast(fmaf(fmaf(x[19], 1e-6f, x[18]), sy1, y[18] * sx1));
            const float ax0 = sy0 * i0, ay0 = sx0 * i0, ax1 = sy1 * i1, ay1 = sx1 * i1;
#pragma unroll
            for (int dp = 0; dp < 2; dp++)
              stsm_x4(pO + srowoff + ((hh * 64 + dp * 32 + lhi) ^ lsw),
                      PBIT0(pack_bf16(fmaf(x[dp * 8], ax0, y[dp * 8] * ay0), fmaf(x[dp * 8 + 1], ax0, y[dp * 8 + 1] * ay0))),
                      PBIT0(pack_bf16(fmaf(x[dp * 8 + 2], ax1, y[dp * 8 + 2] * ay1), fmaf(x[dp * 8 + 3], ax1, y[dp * 8 + 3] * ay1))),
                      PBIT1(pack_bf16(fmaf(x[dp * 8 + 4], ax0, y[dp * 8 + 4] * ay0), fmaf(x[dp * 8 + 5], ax0, y[dp * 8 + 5] * ay0))),
                      PBIT1(pack_bf16(fmaf(x[dp * 8 + 6], ax1, y[dp * 8 + 6] * ay1), fmaf(x[dp * 8 + 7], ax1, y[dp * 8 + 7] * ay1))));
          }
          PUBLISH_O();
          if (XB == 3) { wgmma_wait<0>(); XM_DONE(h == 0); }
          PROFH(20, 34);
          if (h) break;
          if (KVL == 2) { KV_LOAD(1); SCHED_FENCE(); }
          if (!XB) {
            scale32(st, S1 + 32, c0, c1);
            PIN(st, 32);
            LOAD_X();
          }
          if (XB == 4) {
            scale32(st, S1 + 32, c0, c1);
            PIN(st, 32);
            ACC_DEF(T_, 64);
            if (ILV & 2) {
              float e_[16], m_[4];
              KV_LOAD(1);
              mbar_wait(bar_xr, par);
#pragma unroll
              for (int j = 0; j < 8; j++) {
                wgmma_fence();
                wgmma_n16<0>(T_ + j * 8, DESC(dA0 + (OFF_RA >> 4) + (j >> 2) * 1024 + (j & 3) * 2, 0x40000040), make_desc(sbase + OFF_ID, 128, 128) ^ (1ull << 62));
                if (j == 7) wgmma_commit();
                PHI_PIECE(j);
              }
              PHI_FIN();
            } else {
            XM_ISSUE(0); wgmma_commit();
            SCHED_FENCE();
            KV_LOAD(1);
            big = any_big(st);
            }
            SCHED_FENCE();
            PROF(27);
            wgmma_wait<0>(); XM_DONE(true);
            PROF(28);
          }
          if (!(NOBW >> 2 & 1)) bar_wg(wg);
          WSTEP();
          SCHED_FENCE();
          PROF(29);
          if (KVL == 0 && XB != 4) KV_LOAD(1);
          if (XB != 4) big = any_big(st);
          if (KVL == 1) { SCHED_FENCE(); KV_LOAD(1); }
          if (!(ILV & 2)) { phiq_a(st, big); PIN(st, 16); }
          PROF(31);
        }
      }
      __syncwarp();
      if (elect_one()) mbar_arrive_local(bar_epi);
      if (!(NOBW >> 3 & 1)) bar_wg(wg);
#pragma unroll 1
      while (ub < bar_full + 384) {
        WSTEP();
        if (ub == bar_full + 8 * 41) { asm volatile("cp.async.bulk.wait_group.read 0;" ::: "memory"); PROF(35); }
        if (ub == bar_full + 8 * 42) PROF(36);
      }
      {
        float Wb[32];
        LANE_CONSTS();
        TILE_CONSTS(pK, l < NLAYERS - 1, X_BIT(l));
        wgmma_wait<0>();
        ACC_FENCE(S1, 64);
        COPYN(Wb, S1 + 32, 32);
        PROF(37);
        X_OUT(0, S1);
        WARP_STORE(l < NLAYERS - 1 ? &tm_os : &tm_xo, pK, jj * 128, mm * 128 + (l < NLAYERS - 1 ? S_LEN : 0));
        if (l == NLAYERS - 1) { PMASKS(false, 0); X_OUT(1, Wb); break; }
        REL(bar_done + 47 * 8);
        PROF(38);
        if (!(NOBW >> 4 & 1)) bar_wg(wg);
        FIRST_STEP(l + 1);
        PROF(39);
        { PMASKS(false, 0); X_OUT(1, Wb); }
        fence_proxy_async_smem();
      }
    }
    WARP_STORE(&tm_xo, pV, jj * 128 + 64, mm * 128);
    asm volatile("cp.async.bulk.wait_group.read 0;" ::: "memory");
    cluster_sync();
  }
}

typedef CUresult (*PFN_encode)(CUtensorMap*, CUtensorMapDataType, cuuint32_t, void*, const cuuint64_t*, const cuuint64_t*,
                               const cuuint32_t*, const cuuint32_t*, CUtensorMapInterleave, CUtensorMapSwizzle,
                               CUtensorMapL2promotion, CUtensorMapFloatOOBfill);

CUtensorMap make_map(PFN_encode enc, const void* ptr, uint64_t inner, uint64_t outer, uint32_t box_inner, uint32_t box_outer,
                     CUtensorMapSwizzle swz = CU_TENSOR_MAP_SWIZZLE_128B, int promo = CU_TENSOR_MAP_L2_PROMOTION_L2_256B) {
  CUtensorMap m;
  cuuint64_t dims[2] = {inner, outer};
  cuuint64_t strides[1] = {inner * 2};
  cuuint32_t box[2] = {box_inner, box_outer};
  cuuint32_t es[2] = {1, 1};
  enc(&m, CU_TENSOR_MAP_DATA_TYPE_BFLOAT16, 2, const_cast<void*>(ptr), dims, strides, box, es, CU_TENSOR_MAP_INTERLEAVE_NONE,
      swz, (CUtensorMapL2promotion)promo, CU_TENSOR_MAP_FLOAT_OOB_FILL_NONE);
  return m;
}

}

extern "C" void kernel_launch(void* const* d_in, const int* in_sizes, int n_in, void* d_out, int out_size) {
  (void)in_sizes; (void)n_in; (void)out_size;
  static PFN_encode enc = nullptr;
  if (!enc) {
    void* fn = nullptr;
    cudaDriverEntryPointQueryResult qr;
    cudaGetDriverEntryPoint("cuTensorMapEncodeTiled", &fn, cudaEnableDefault, &qr);
    enc = (PFN_encode)fn;
    cudaFuncSetAttribute(mega_kernel, cudaFuncAttributeMaxDynamicSharedMemorySize, SMEM_BYTES);
  }
  Params prm;
  prm.x0 = (const __nv_bfloat16*)d_in[0];
  prm.wA_qkv = (const __nv_bfloat16*)d_in[1];
  prm.wA_o = (const __nv_bfloat16*)d_in[2];
  prm.wB_qkv = (const __nv_bfloat16*)d_in[4];
  prm.wB_phi = (const __nv_bfloat16*)d_in[5];
  prm.wB_o = (const __nv_bfloat16*)d_in[6];
  prm.out = (__nv_bfloat16*)d_out;
  void *obuf = nullptr, *wf = nullptr;
  cudaGetSymbolAddress(&obuf, g_obuf);
  cudaGetSymbolAddress(&wf, g_wfold);
  CUtensorMap tm_x0 = make_map(enc, d_in[0], D_MODEL, S_LEN, 64, 128, CU_TENSOR_MAP_SWIZZLE_128B, XPROMO);
  CUtensorMap tm_xo = make_map(enc, d_out, D_MODEL, S_LEN, 64, 16);
  CUtensorMap tm_os = make_map(enc, obuf, D_MODEL, 2 * S_LEN, 64, 16);
  CUtensorMap tm_o = make_map(enc, obuf, D_MODEL, 2 * S_LEN, 64, 128, CU_TENSOR_MAP_SWIZZLE_128B, OPROMO);
  CUtensorMap tm_wf = make_map(enc, wf, 2048, D_MODEL, 64, 32);
  CUtensorMap tm_wqA = make_map(enc, d_in[1], 3 * D_MODEL, D_MODEL, 64, 32, CU_TENSOR_MAP_SWIZZLE_128B, WPROMO);
  CUtensorMap tm_wqB = make_map(enc, prm.wB_qkv, 3 * D_MODEL, D_MODEL, 64, 32);
  CUtensorMap tm_woA = make_map(enc, prm.wA_o, D_MODEL, D_MODEL, 64, 64);
  CUtensorMap tm_woB = make_map(enc, prm.wB_o, D_MODEL, D_MODEL, 64, 64);
  CUtensorMap tm_phi = make_map(enc, prm.wB_phi, 32, 1024, 32, 128, CU_TENSOR_MAP_SWIZZLE_64B);
  mega_kernel<<<NMAIN + NAUX, 384, SMEM_BYTES>>>(tm_x0, tm_xo, tm_os, tm_o, tm_wf, tm_wqA, tm_wqB, tm_woA, tm_woB, tm_phi, prm);
}
```

```cpp
#include <cuda_runtime.h>
#include <cuda.h>
#include <cuda_bf16.h>
#include <stdint.h>

#define NLAYERS 4

#define STAG1 0
#define HPUMP1 2
#define HPUMP2 1
#define ASKEW 2
#define FPUMP 3
#define PFGAP 100
#define POLLGAP 120
#define OW 1
#define AW0 1
#define RLATE 3
#define FSTART 0
#define MAPV 1
#define HW1 29
#define XPACE 0x06050401000000ull
#define XP0 4
#define HW0 18
#define XD 4
#define WFGAP 50
#define KT0 2
#define W23 0
#define AX 0
#define PF0 1
#define ORD 0
#define EARLY (2 + ORD)
#define UPS(u) (ORD ? (u) & 1 : (u) >> 1)
#define USL(u) (ORD ? (u) >> 1 : (u) & 1)
#define BIGLIM 3600.f
#define SUMLO 0x1p-100f
#define SUMHI 0x1p100f
#define EROT 1
#define FINW 0
#define AHOIST 1
#define EMRG 1
#define XPROMO 2
#define OPROMO 3
#define STAG2 300
#define WPROMO 3
#define SB0 2
#define SB1 4
#define SB2 6
#define KVL 2
#define BMASK 0x1F
#define ASITE 1
#define NEWOPTS
#define NEWO 3
#define PROWS 3
#define HSL 0
#define HDEL 0
#define HDEL1 0
#define SPD0 0
#define SPD1 0
#define SPD2 300
#define FRB 0x3535353535ull
#define NOB 0xFFFFFF00u
#define NO1 ~0u
#define NOX ~0u
#define ILV 1
#define SEARLY 0
#define PAIR 2
#define PPOS 1
#define PPOS0 1
#define NOBW 0
#define CPA 0
#define PFW 0
#define FD0 0
#define FD1 3
#define RPACE 0x221100
#define XA 0
#define XB 4
#define XMMA 1
namespace {

constexpr int S_LEN = 2048, D_MODEL = 1024;
constexpr int NAUX = 4, NMAIN = 128;
constexpr int SLOT = 16384;
constexpr int QST = 24576;
constexpr int OFF_RA = 6 * SLOT, OFF_S = 10 * SLOT;
constexpr int OFF_HALO = 13 * SLOT, OFF_LNB = OFF_HALO  , OFF_ONES = OFF_HALO + 3072;
constexpr int OFF_ST = OFF_HALO + 7168  , OFF_ID = OFF_HALO + 7680, OFF_PHI = OFF_HALO + 8192;
constexpr int OFF_BAR = 14 * SLOT;
constexpr int OFF_LNA = OFF_BAR + 1024;
constexpr int SMEM_BYTES = OFF_LNA + 2048;
#define WO_ASLOT(par) ((par) ? 0x9876CAB39876CA98ull : 0x98C76BA398C7698Cull)
constexpr unsigned long long WO_BSLOT = 0x5432105421054210ull;
__device__ __forceinline__ int srcb(int j, int i) { return (i + (i >= j)) & 7; }
__device__ __forceinline__ int kslice(int j, int i) { return i < 2 ? 2 * j + i : (i < 9 ? 2 * srcb(j, i - 2) : 2 * srcb(j, i - 9) + 1); }
__device__ __forceinline__ int wslice(int j, int s) { return 2 * ((s & 7) ? srcb(j, (s & 7) - 1) : j) + (s >> 3); }
constexpr int KVH = 6 * 128 * 4;

struct __align__(128) Flag { unsigned v; unsigned pad[31]; };
struct Flags {
  Flag xready[4][16];
  Flag wfready[8];
  Flag done;
  Flag epoch;
};

__device__ Flags g_flags;
__device__ __nv_bfloat16 g_obuf[2 * S_LEN * D_MODEL];
#define O_BIT(l) ((epoch * NLAYERS + (l) + 1) & 1u)
#define X_BIT(l) ((epoch * (NLAYERS - 1) + (l) + 1) & 1u)
__device__ __nv_bfloat16 g_wfold[D_MODEL * 2048];
__device__ uint4 g_halo[16 * 8 * 512];
__device__ __align__(128) float g_kv[2][32 * KVH];
__device__ __align__(128) uint2 g_colsum[2][1536][2];
__device__ __align__(128) uint2 g_stats[S_LEN * 8];
#define H_BIT(l) (NLAYERS > 2 ? (uint32_t)((l) == 0) : (ep1 & 1))
#define STAT_TAG(l) ((ep1 * NLAYERS + (l) + 1) & 3u)

#define RETRY_COUNT()
#define PRL 0
#define PRU 0
#define PROFL 1
#define PROFW 0
#define PROFT(i) do {} while (0)
#define PROF(i) do {} while (0)
#define PROFH(i, j) do {} while (0)

__device__ __forceinline__ uint32_t smem_u32(const void* p) { return (uint32_t)__cvta_generic_to_shared(p); }
__device__ __forceinline__ bool elect_one() {
  uint32_t p;
  asm volatile("{\n.reg .pred p;\nelect.sync _|p, 0xffffffff;\nselp.u32 %0, 1, 0, p;\n}\n" : "=r"(p));
  return p != 0;
}
__device__ __forceinline__ void mbar_init(uint32_t bar, uint32_t cnt) {
  asm volatile("mbarrier.init.shared::cta.b64 [%0], %1;" :: "r"(bar), "r"(cnt));
}
__device__ __forceinline__ void mbar_expect_tx(uint32_t bar, uint32_t bytes) {
  asm volatile("mbarrier.arrive.expect_tx.shared::cta.b64 _, [%0], %1;" :: "r"(bar), "r"(bytes) : "memory");
}
#define mbar_wait(bar, parity) \
  asm volatile("{\n.reg .pred p, q;\nW_%=:\nmbarrier.try_wait.parity.shared::cta.b64 p, [%1], %2;\nadd.s32 %0, %0, -1;\n" \
               "setp.gt.and.s32 q, %0, 0, !p;\n@q bra.uni W_%=;\n}\n" : "+r"(budget) : "r"((uint32_t)(bar)), "r"((uint32_t)(parity)) : "memory")
#define mbar_wait_sl(bar, parity) \
  asm volatile("{\n.reg .pred p, q;\nW_%=:\nmbarrier.try_wait.parity.shared::cta.b64 p, [%1], %2, 20000;\nadd.s32 %0, %0, -64;\n" \
               "setp.gt.and.s32 q, %0, 0, !p;\n@q bra.uni W_%=;\n}\n" : "+r"(budget) : "r"((uint32_t)(bar)), "r"((uint32_t)(parity)) : "memory")
__device__ __forceinline__ void mbar_arrive_local(uint32_t bar) {
  asm volatile("mbarrier.arrive.shared::cta.b64 _, [%0];" :: "r"(bar) : "memory");
}
__device__ __forceinline__ void tma_load_2d(uint32_t dst, const CUtensorMap* tm, uint32_t bar, int c0, int c1) {
  asm volatile("cp.async.bulk.tensor.2d.shared::cluster.global.mbarrier::complete_tx::bytes [%0], [%1, {%3, %4}], [%2];"
               :: "r"(dst), "l"(tm), "r"(bar), "r"(c0), "r"(c1) : "memory");
}
__device__ __forceinline__ void tma_load_2d_mc(uint32_t dst, const CUtensorMap* tm, uint32_t bar, int c0, int c1) {
  asm volatile("cp.async.bulk.tensor.2d.shared::cluster.global.mbarrier::complete_tx::bytes.multicast::cluster [%0], [%1, {%3, %4}], [%2], %5;"
               :: "r"(dst), "l"(tm), "r"(bar), "r"(c0), "r"(c1), "h"((uint16_t)3) : "memory");
}
__device__ __forceinline__ void tma_store_2d(const CUtensorMap* tm, uint32_t src, int c0, int c1) {
  asm volatile("cp.async.bulk.tensor.2d.global.shared::cta.bulk_group [%0, {%2, %3}], [%1];"
               :: "l"(tm), "r"(src), "r"(c0), "r"(c1) : "memory");
}
__device__ __forceinline__ void bulk_commit_wait() {
  asm volatile("cp.async.bulk.commit_group;\ncp.async.bulk.wait_group 0;" ::: "memory");
}
__device__ __forceinline__ void prefetch_tmap(const CUtensorMap* tm) {
  asm volatile("prefetch.tensormap [%0];" :: "l"(tm) : "memory");
}
__device__ __forceinline__ void fence_proxy_async_global() { asm volatile("fence.proxy.async.global;" ::: "memory"); }
__device__ __forceinline__ void fence_proxy_async_smem() { asm volatile("fence.proxy.async.shared::cta;" ::: "memory"); }
__device__ __forceinline__ unsigned ld_relaxed(const unsigned* p) {
  unsigned v;
  asm volatile("ld.relaxed.gpu.global.u32 %0, [%1];" : "=r"(v) : "l"(p) : "memory");
  return v;
}
__device__ __forceinline__ void fence_acquire() { asm volatile("fence.acquire.gpu;" ::: "memory"); }
__device__ __forceinline__ void wait_flag(const unsigned* p, unsigned target) {
  int it = 0;
  while ((int)(ld_relaxed(p) - target) < 0 && ++it < (1 << 20)) {}
  fence_acquire();
}
__device__ __forceinline__ void signal_release(unsigned* p) {
  asm volatile("red.release.gpu.global.add.u32 [%0], 1;" :: "l"(p) : "memory");
}
template <int ID, int N> __device__ __forceinline__ void bar_arrive() { asm volatile("bar.arrive %0, %1;" :: "n"(ID), "n"(N) : "memory"); }
template <int ID, int N> __device__ __forceinline__ void bar_sync() { asm volatile("bar.sync %0, %1;" :: "n"(ID), "n"(N) : "memory"); }
__device__ __forceinline__ void bar_wg(int wg) { asm volatile("bar.sync %0, 128;" :: "r"(2 + wg) : "memory"); }
__device__ __forceinline__ void cluster_sync() {
  asm volatile("barrier.cluster.arrive.relaxed.aligned;\nbarrier.cluster.wait.aligned;" ::: "memory");
}
__device__ __forceinline__ void cluster_wait() { asm volatile("barrier.cluster.wait.acquire.aligned;" ::: "memory"); }
enum { BAR_X1 = 7, BAR_WF = 8  , BAR_SKEW = 10 };

__device__ __forceinline__ void wgmma_fence() { asm volatile("wgmma.fence.sync.aligned;" ::: "memory"); }
__device__ __forceinline__ void wgmma_commit() { asm volatile("wgmma.commit_group.sync.aligned;" ::: "memory"); }
template <int N> __device__ __forceinline__ void wgmma_wait() { asm volatile("wgmma.wait_group.sync.aligned %0;" :: "n"(N) : "memory"); }

template <int scale_d, int tnsp_b = 1> __device__ __forceinline__ void wgmma_n192(float* d, uint64_t descA, uint64_t descB) {
  asm volatile("{\n.reg .pred p;\nsetp.ne.b32 p, %98, 0;\n"
               "wgmma.mma_async.sync.aligned.m64n192k16.f32.bf16.bf16 {%0,%1,%2,%3,%4,%5,%6,%7,%8,%9,%10,%11,%12,%13,%14,%15,%16,%17,%18,%19,%20,%21,%22,%23,%24,%25,%26,%27,%28,%29,%30,%31,%32,%33,%34,%35,%36,%37,%38,%39,%40,%41,%42,%43,%44,%45,%46,%47,%48,%49,%50,%51,%52,%53,%54,%55,%56,%57,%58,%59,%60,%61,%62,%63,%64,%65,%66,%67,%68,%69,%70,%71,%72,%73,%74,%75,%76,%77,%78,%79,%80,%81,%82,%83,%84,%85,%86,%87,%88,%89,%90,%91,%92,%93,%94,%95}, %96, %97, p, 1, 1, 0, %99;\n}\n"
               : "+f"(d[0]), "+f"(d[1]), "+f"(d[2]), "+f"(d[3]), "+f"(d[4]), "+f"(d[5]), "+f"(d[6]), "+f"(d[7]), "+f"(d[8]), "+f"(d[9]), "+f"(d[10]), "+f"(d[11]), "+f"(d[12]), "+f"(d[13]), "+f"(d[14]), "+f"(d[15]), "+f"(d[16]), "+f"(d[17]), "+f"(d[18]), "+f"(d[19]), "+f"(d[20]), "+f"(d[21]), "+f"(d[22]), "+f"(d[23]), "+f"(d[24]), "+f"(d[25]), "+f"(d[26]), "+f"(d[27]), "+f"(d[28]), "+f"(d[29]), "+f"(d[30]), "+f"(d[31]), "+f"(d[32]), "+f"(d[33]), "+f"(d[34]), "+f"(d[35]), "+f"(d[36]), "+f"(d[37]), "+f"(d[38]), "+f"(d[39]), "+f"(d[40]), "+f"(d[41]), "+f"(d[42]), "+f"(d[43]), "+f"(d[44]), "+f"(d[45]), "+f"(d[46]), "+f"(d[47]), "+f"(d[48]), "+f"(d[49]), "+f"(d[50]), "+f"(d[51]), "+f"(d[52]), "+f"(d[53]), "+f"(d[54]), "+f"(d[55]), "+f"(d[56]), "+f"(d[57]), "+f"(d[58]), "+f"(d[59]), "+f"(d[60]), "+f"(d[61]), "+f"(d[62]), "+f"(d[63]), "+f"(d[64]), "+f"(d[65]), "+f"(d[66]), "+f"(d[67]), "+f"(d[68]), "+f"(d[69]), "+f"(d[70]), "+f"(d[71]), "+f"(d[72]), "+f"(d[73]), "+f"(d[74]), "+f"(d[75]), "+f"(d[76]), "+f"(d[77]), "+f"(d[78]), "+f"(d[79]), "+f"(d[80]), "+f"(d[81]), "+f"(d[82]), "+f"(d[83]), "+f"(d[84]), "+f"(d[85]), "+f"(d[86]), "+f"(d[87]), "+f"(d[88]), "+f"(d[89]), "+f"(d[90]), "+f"(d[91]), "+f"(d[92]), "+f"(d[93]), "+f"(d[94]), "+f"(d[95])
               : "l"(descA), "l"(descB), "n"(scale_d), "n"(tnsp_b));
}
template <int scale_d> __device__ __forceinline__ void wgmma4_n192(float* d, uint32_t da, uint32_t db) {
#define R_ "{%0,%1,%2,%3,%4,%5,%6,%7,%8,%9,%10,%11,%12,%13,%14,%15,%16,%17,%18,%19,%20,%21,%22,%23,%24,%25,%26,%27,%28,%29,%30,%31,%32,%33,%34,%35,%36,%37,%38,%39,%40,%41,%42,%43,%44,%45,%46,%47,%48,%49,%50,%51,%52,%53,%54,%55,%56,%57,%58,%59,%60,%61,%62,%63,%64,%65,%66,%67,%68,%69,%70,%71,%72,%73,%74,%75,%76,%77,%78,%79,%80,%81,%82,%83,%84,%85,%86,%87,%88,%89,%90,%91,%92,%93,%94,%95}"
  asm volatile("{\n.reg .pred p, q;\n.reg .b64 a, b;\nsetp.ne.b32 p, %98, 0;\nsetp.eq.b32 q, 0, 0;\nmov.b64 a, {%96, 0x40000040};\nmov.b64 b, {%97, 0x40000040};\n"
               "wgmma.mma_async.sync.aligned.m64n192k16.f32.bf16.bf16 " R_ ", a, b, p, 1, 1, 0, 1;\nadd.s64 a, a, 2;\nadd.s64 b, b, 128;\n"
               "wgmma.mma_async.sync.aligned.m64n192k16.f32.bf16.bf16 " R_ ", a, b, q, 1, 1, 0, 1;\nadd.s64 a, a, 2;\nadd.s64 b, b, 128;\n"
               "wgmma.mma_async.sync.aligned.m64n192k16.f32.bf16.bf16 " R_ ", a, b, q, 1, 1, 0, 1;\nadd.s64 a, a, 2;\nadd.s64 b, b, 128;\n"
               "wgmma.mma_async.sync.aligned.m64n192k16.f32.bf16.bf16 " R_ ", a, b, q, 1, 1, 0, 1;\n}\n"
               : "+f"(d[0]), "+f"(d[1]), "+f"(d[2]), "+f"(d[3]), "+f"(d[4]), "+f"(d[5]), "+f"(d[6]), "+f"(d[7]), "+f"(d[8]), "+f"(d[9]), "+f"(d[10]), "+f"(d[11]), "+f"(d[12]), "+f"(d[13]), "+f"(d[14]), "+f"(d[15]), "+f"(d[16]), "+f"(d[17]), "+f"(d[18]), "+f"(d[19]), "+f"(d[20]), "+f"(d[21]), "+f"(d[22]), "+f"(d[23]), "+f"(d[24]), "+f"(d[25]), "+f"(d[26]), "+f"(d[27]), "+f"(d[28]), "+f"(d[29]), "+f"(d[30]), "+f"(d[31]), "+f"(d[32]), "+f"(d[33]), "+f"(d[34]), "+f"(d[35]), "+f"(d[36]), "+f"(d[37]), "+f"(d[38]), "+f"(d[39]), "+f"(d[40]), "+f"(d[41]), "+f"(d[42]), "+f"(d[43]), "+f"(d[44]), "+f"(d[45]), "+f"(d[46]), "+f"(d[47]), "+f"(d[48]), "+f"(d[49]), "+f"(d[50]), "+f"(d[51]), "+f"(d[52]), "+f"(d[53]), "+f"(d[54]), "+f"(d[55]), "+f"(d[56]), "+f"(d[57]), "+f"(d[58]), "+f"(d[59]), "+f"(d[60]), "+f"(d[61]), "+f"(d[62]), "+f"(d[63]), "+f"(d[64]), "+f"(d[65]), "+f"(d[66]), "+f"(d[67]), "+f"(d[68]), "+f"(d[69]), "+f"(d[70]), "+f"(d[71]), "+f"(d[72]), "+f"(d[73]), "+f"(d[74]), "+f"(d[75]), "+f"(d[76]), "+f"(d[77]), "+f"(d[78]), "+f"(d[79]), "+f"(d[80]), "+f"(d[81]), "+f"(d[82]), "+f"(d[83]), "+f"(d[84]), "+f"(d[85]), "+f"(d[86]), "+f"(d[87]), "+f"(d[88]), "+f"(d[89]), "+f"(d[90]), "+f"(d[91]), "+f"(d[92]), "+f"(d[93]), "+f"(d[94]), "+f"(d[95])
               : "r"(da), "r"(db), "n"(scale_d));
#undef R_
}
template <int scale_d> __device__ __forceinline__ void wgmma4_n128(float* d, uint32_t da, uint32_t db) {
#define R_ "{%0,%1,%2,%3,%4,%5,%6,%7,%8,%9,%10,%11,%12,%13,%14,%15,%16,%17,%18,%19,%20,%21,%22,%23,%24,%25,%26,%27,%28,%29,%30,%31,%32,%33,%34,%35,%36,%37,%38,%39,%40,%41,%42,%43,%44,%45,%46,%47,%48,%49,%50,%51,%52,%53,%54,%55,%56,%57,%58,%59,%60,%61,%62,%63}"
  asm volatile("{\n.reg .pred p, q;\n.reg .b64 a, b;\nsetp.ne.b32 p, %66, 0;\nsetp.eq.b32 q, 0, 0;\nmov.b64 a, {%64, 0x40000040};\nmov.b64 b, {%65, 0x40000040};\n"
               "wgmma.mma_async.sync.aligned.m64n128k16.f32.bf16.bf16 " R_ ", a, b, p, 1, 1, 0, 1;\nadd.s64 a, a, 2;\nadd.s64 b, b, 128;\n"
               "wgmma.mma_async.sync.aligned.m64n128k16.f32.bf16.bf16 " R_ ", a, b, q, 1, 1, 0, 1;\nadd.s64 a, a, 2;\nadd.s64 b, b, 128;\n"
               "wgmma.mma_async.sync.aligned.m64n128k16.f32.bf16.bf16 " R_ ", a, b, q, 1, 1, 0, 1;\nadd.s64 a, a, 2;\nadd.s64 b, b, 128;\n"
               "wgmma.mma_async.sync.aligned.m64n128k16.f32.bf16.bf16 " R_ ", a, b, q, 1, 1, 0, 1;\n}\n"
               : "+f"(d[0]), "+f"(d[1]), "+f"(d[2]), "+f"(d[3]), "+f"(d[4]), "+f"(d[5]), "+f"(d[6]), "+f"(d[7]), "+f"(d[8]), "+f"(d[9]), "+f"(d[10]), "+f"(d[11]), "+f"(d[12]), "+f"(d[13]), "+f"(d[14]), "+f"(d[15]), "+f"(d[16]), "+f"(d[17]), "+f"(d[18]), "+f"(d[19]), "+f"(d[20]), "+f"(d[21]), "+f"(d[22]), "+f"(d[23]), "+f"(d[24]), "+f"(d[25]), "+f"(d[26]), "+f"(d[27]), "+f"(d[28]), "+f"(d[29]), "+f"(d[30]), "+f"(d[31]), "+f"(d[32]), "+f"(d[33]), "+f"(d[34]), "+f"(d[35]), "+f"(d[36]), "+f"(d[37]), "+f"(d[38]), "+f"(d[39]), "+f"(d[40]), "+f"(d[41]), "+f"(d[42]), "+f"(d[43]), "+f"(d[44]), "+f"(d[45]), "+f"(d[46]), "+f"(d[47]), "+f"(d[48]), "+f"(d[49]), "+f"(d[50]), "+f"(d[51]), "+f"(d[52]), "+f"(d[53]), "+f"(d[54]), "+f"(d[55]), "+f"(d[56]), "+f"(d[57]), "+f"(d[58]), "+f"(d[59]), "+f"(d[60]), "+f"(d[61]), "+f"(d[62]), "+f"(d[63])
               : "r"(da), "r"(db), "n"(scale_d));
#undef R_
}
template <int scale_d> __device__ __forceinline__ void wgmma_n32(float* d, uint64_t descA, uint64_t descB) {
  asm volatile("{\n.reg .pred p;\nsetp.ne.b32 p, %18, 0;\n"
               "wgmma.mma_async.sync.aligned.m64n32k16.f32.bf16.bf16 {%0,%1,%2,%3,%4,%5,%6,%7,%8,%9,%10,%11,%12,%13,%14,%15}, %16, %17, p, 1, 1, 0, 1;\n}\n"
               : "+f"(d[0]), "+f"(d[1]), "+f"(d[2]), "+f"(d[3]), "+f"(d[4]), "+f"(d[5]), "+f"(d[6]), "+f"(d[7]), "+f"(d[8]), "+f"(d[9]), "+f"(d[10]), "+f"(d[11]), "+f"(d[12]), "+f"(d[13]), "+f"(d[14]), "+f"(d[15])
               : "l"(descA), "l"(descB), "n"(scale_d));
}
template <int scale_d> __device__ __forceinline__ void wgmma_n16(float* d, uint64_t descA, uint64_t descB) {
  asm volatile("{\n.reg .pred p;\nsetp.ne.b32 p, %10, 0;\n"
               "wgmma.mma_async.sync.aligned.m64n16k16.f32.bf16.bf16 {%0,%1,%2,%3,%4,%5,%6,%7}, %8, %9, p, 1, 1, 0, 0;\n}\n"
               : "+f"(d[0]), "+f"(d[1]), "+f"(d[2]), "+f"(d[3]), "+f"(d[4]), "+f"(d[5]), "+f"(d[6]), "+f"(d[7])
               : "l"(descA), "l"(descB), "n"(scale_d));
}
template <int scale_d, int tnsp_a> __device__ __forceinline__ void wgmma_n40(float* d, uint64_t descA, uint64_t descB) {
  asm volatile("{\n.reg .pred p;\nsetp.ne.b32 p, %22, 0;\n"
               "wgmma.mma_async.sync.aligned.m64n40k16.f32.bf16.bf16 {%0,%1,%2,%3,%4,%5,%6,%7,%8,%9,%10,%11,%12,%13,%14,%15,%16,%17,%18,%19}, %20, %21, p, 1, 1, %23, 1;\n}\n"
               : "+f"(d[0]), "+f"(d[1]), "+f"(d[2]), "+f"(d[3]), "+f"(d[4]), "+f"(d[5]), "+f"(d[6]), "+f"(d[7]), "+f"(d[8]), "+f"(d[9]), "+f"(d[10]), "+f"(d[11]), "+f"(d[12]), "+f"(d[13]), "+f"(d[14]), "+f"(d[15]), "+f"(d[16]), "+f"(d[17]), "+f"(d[18]), "+f"(d[19])
               : "l"(descA), "l"(descB), "n"(scale_d), "n"(tnsp_a));
}
template <int scale_d> __device__ __forceinline__ void wgmma_n40_rs(float* d, const uint32_t* a, uint64_t descB) {
  asm volatile("{\n.reg .pred p;\nsetp.ne.b32 p, %25, 0;\n"
               "wgmma.mma_async.sync.aligned.m64n40k16.f32.bf16.bf16 {%0,%1,%2,%3,%4,%5,%6,%7,%8,%9,%10,%11,%12,%13,%14,%15,%16,%17,%18,%19}, {%20,%21,%22,%23}, %24, p, 1, 1, 1;\n}\n"
               : "+f"(d[0]), "+f"(d[1]), "+f"(d[2]), "+f"(d[3]), "+f"(d[4]), "+f"(d[5]), "+f"(d[6]), "+f"(d[7]), "+f"(d[8]), "+f"(d[9]), "+f"(d[10]), "+f"(d[11]), "+f"(d[12]), "+f"(d[13]), "+f"(d[14]), "+f"(d[15]), "+f"(d[16]), "+f"(d[17]), "+f"(d[18]), "+f"(d[19])
               : "r"(a[0]), "r"(a[1]), "r"(a[2]), "r"(a[3]), "l"(descB), "n"(scale_d));
}
__device__ __forceinline__ void wgmma_copy(float* d, uint32_t da, uint64_t descB, int keep) {
  asm volatile("{\n.reg .pred p;\n.reg .b64 a;\nsetp.ne.b32 p, %66, 0;\nmov.b64 a, {%64, 0x40000040};\n"
               "wgmma.mma_async.sync.aligned.m64n16k16.f32.bf16.bf16 {%0,%1,%2,%3,%4,%5,%6,%7}, a, %65, p, 1, 1, 0, 0;\nadd.s64 a, a, 2;\n"
               "wgmma.mma_async.sync.aligned.m64n16k16.f32.bf16.bf16 {%8,%9,%10,%11,%12,%13,%14,%15}, a, %65, p, 1, 1, 0, 0;\nadd.s64 a, a, 2;\n"
               "wgmma.mma_async.sync.aligned.m64n16k16.f32.bf16.bf16 {%16,%17,%18,%19,%20,%21,%22,%23}, a, %65, p, 1, 1, 0, 0;\nadd.s64 a, a, 2;\n"
               "wgmma.mma_async.sync.aligned.m64n16k16.f32.bf16.bf16 {%24,%25,%26,%27,%28,%29,%30,%31}, a, %65, p, 1, 1, 0, 0;\nadd.s64 a, a, 1018;\n"
               "wgmma.mma_async.sync.aligned.m64n16k16.f32.bf16.bf16 {%32,%33,%34,%35,%36,%37,%38,%39}, a, %65, p, 1, 1, 0, 0;\nadd.s64 a, a, 2;\n"
               "wgmma.mma_async.sync.aligned.m64n16k16.f32.bf16.bf16 {%40,%41,%42,%43,%44,%45,%46,%47}, a, %65, p, 1, 1, 0, 0;\nadd.s64 a, a, 2;\n"
               "wgmma.mma_async.sync.aligned.m64n16k16.f32.bf16.bf16 {%48,%49,%50,%51,%52,%53,%54,%55}, a, %65, p, 1, 1, 0, 0;\nadd.s64 a, a, 2;\n"
               "wgmma.mma_async.sync.aligned.m64n16k16.f32.bf16.bf16 {%56,%57,%58,%59,%60,%61,%62,%63}, a, %65, p, 1, 1, 0, 0;\n"
               "}\n"
               : "+f"(d[0]), "+f"(d[1]), "+f"(d[2]), "+f"(d[3]), "+f"(d[4]), "+f"(d[5]), "+f"(d[6]), "+f"(d[7]), "+f"(d[8]), "+f"(d[9]), "+f"(d[10]), "+f"(d[11]), "+f"(d[12]), "+f"(d[13]), "+f"(d[14]), "+f"(d[15]), "+f"(d[16]), "+f"(d[17]), "+f"(d[18]), "+f"(d[19]), "+f"(d[20]), "+f"(d[21]), "+f"(d[22]), "+f"(d[23]), "+f"(d[24]), "+f"(d[25]), "+f"(d[26]), "+f"(d[27]), "+f"(d[28]), "+f"(d[29]), "+f"(d[30]), "+f"(d[31]), "+f"(d[32]), "+f"(d[33]), "+f"(d[34]), "+f"(d[35]), "+f"(d[36]), "+f"(d[37]), "+f"(d[38]), "+f"(d[39]), "+f"(d[40]), "+f"(d[41]), "+f"(d[42]), "+f"(d[43]), "+f"(d[44]), "+f"(d[45]), "+f"(d[46]), "+f"(d[47]), "+f"(d[48]), "+f"(d[49]), "+f"(d[50]), "+f"(d[51]), "+f"(d[52]), "+f"(d[53]), "+f"(d[54]), "+f"(d[55]), "+f"(d[56]), "+f"(d[57]), "+f"(d[58]), "+f"(d[59]), "+f"(d[60]), "+f"(d[61]), "+f"(d[62]), "+f"(d[63])
               : "r"(da), "l"(descB), "r"(keep));
}
__device__ __forceinline__ uint64_t make_desc(uint32_t addr, uint32_t lbo_bytes, uint32_t sbo_bytes) {
  return (uint64_t)((addr & 0x3FFFF) >> 4) | ((uint64_t)(lbo_bytes >> 4) << 16) | ((uint64_t)(sbo_bytes >> 4) << 32) | (1ull << 62);
}

__device__ __forceinline__ void ldsm_x4(uint32_t addr, uint32_t& r0, uint32_t& r1, uint32_t& r2, uint32_t& r3) {
  asm volatile("ldmatrix.sync.aligned.m8n8.x4.shared.b16 {%0,%1,%2,%3}, [%4];" : "=r"(r0), "=r"(r1), "=r"(r2), "=r"(r3) : "r"(addr) : "memory");
}
__device__ __forceinline__ void ldsm_x4_t(uint32_t addr, uint32_t& r0, uint32_t& r1, uint32_t& r2, uint32_t& r3) {
  asm volatile("ldmatrix.sync.aligned.m8n8.x4.trans.shared.b16 {%0,%1,%2,%3}, [%4];" : "=r"(r0), "=r"(r1), "=r"(r2), "=r"(r3) : "r"(addr) : "memory");
}
__device__ __forceinline__ void stsm_x4(uint32_t addr, uint32_t r0, uint32_t r1, uint32_t r2, uint32_t r3) {
  asm volatile("stmatrix.sync.aligned.m8n8.x4.shared.b16 [%0], {%1,%2,%3,%4};" :: "r"(addr), "r"(r0), "r"(r1), "r"(r2), "r"(r3) : "memory");
}
__device__ __forceinline__ void sts128(uint32_t addr, uint32_t a, uint32_t b, uint32_t c, uint32_t d) {
  asm volatile("st.shared.v4.u32 [%0], {%1,%2,%3,%4};" :: "r"(addr), "r"(a), "r"(b), "r"(c), "r"(d) : "memory");
}
__device__ __forceinline__ float lds32f(uint32_t addr) {
  float v;
  asm volatile("ld.shared.f32 %0, [%1];" : "=f"(v) : "r"(addr) : "memory");
  return v;
}
__device__ __forceinline__ void sts32f(uint32_t addr, float a) {
  asm volatile("st.shared.f32 [%0], %1;" :: "r"(addr), "f"(a) : "memory");
}
__device__ __forceinline__ void mma_bf16(float (&c)[4], uint32_t a0, uint32_t a1, uint32_t a2, uint32_t a3, uint32_t b0, uint32_t b1) {
  asm volatile("mma.sync.aligned.m16n8k16.row.col.f32.bf16.bf16.f32 {%0,%1,%2,%3}, {%4,%5,%6,%7}, {%8,%9}, {%0,%1,%2,%3};"
               : "+f"(c[0]), "+f"(c[1]), "+f"(c[2]), "+f"(c[3]) : "r"(a0), "r"(a1), "r"(a2), "r"(a3), "r"(b0), "r"(b1));
}
__device__ __forceinline__ void mma_bf16_z(float (&c)[4], uint32_t a0, uint32_t a1, uint32_t a2, uint32_t a3, uint32_t b0, uint32_t b1) {
  asm volatile("mma.sync.aligned.m16n8k16.row.col.f32.bf16.bf16.f32 {%0,%1,%2,%3}, {%4,%5,%6,%7}, {%8,%9}, {%10,%10,%10,%10};"
               : "=f"(c[0]), "=f"(c[1]), "=f"(c[2]), "=f"(c[3]) : "r"(a0), "r"(a1), "r"(a2), "r"(a3), "r"(b0), "r"(b1), "f"(0.f));
}
__device__ __forceinline__ uint32_t movm_t(uint32_t v) {
  uint32_t r;
  asm volatile("movmatrix.sync.aligned.m8n8.trans.b16 %0, %1;" : "=r"(r) : "r"(v));
  return r;
}
__device__ __forceinline__ uint32_t pack_bf16(float lo, float hi) {
  uint32_t r;
  asm("cvt.rn.bf16x2.f32 %0, %1, %2;" : "=r"(r) : "f"(hi), "f"(lo));
  return r;
}
__device__ __forceinline__ float bf_lo(uint32_t v) { return __uint_as_float(v << 16); }
__device__ __forceinline__ float bf_hi(uint32_t v) { return __uint_as_float(v & 0xFFFF0000u); }
__device__ __forceinline__ void split3(float x, uint32_t& h, uint32_t& m, uint32_t& l) {
  h = pack_bf16(x, 0.f); x -= bf_lo(h);
  m = pack_bf16(x, 0.f); x -= bf_lo(m);
  l = pack_bf16(x, 0.f);
}
__device__ __forceinline__ float ex2(float x) { float r; asm("ex2.approx.ftz.f32 %0, %1;" : "=f"(r) : "f"(x)); return r; }
__device__ __forceinline__ float rcp_fast(float x) { float r; asm("rcp.approx.ftz.f32 %0, %1;" : "=f"(r) : "f"(x)); return r; }
__device__ __forceinline__ void red_v4(float* p, float a, float b, float c, float d) {
  asm volatile("red.global.add.v4.f32 [%0], {%1, %2, %3, %4};" :: "l"(p), "f"(a), "f"(b), "f"(c), "f"(d) : "memory");
}
__device__ __forceinline__ uint4 ld_ll(const uint4* p) {
  uint4 v;
  asm volatile("{\n.reg .b64 a, b;\nld.relaxed.gpu.global.v2.b64 {a, b}, [%4];\nmov.b64 {%0, %1}, a;\nmov.b64 {%2, %3}, b;\n}\n"
               : "=r"(v.x), "=r"(v.y), "=r"(v.z), "=r"(v.w) : "l"(p) : "memory");
  return v;
}
__device__ __forceinline__ void st_b64(uint2* p, uint32_t a, uint32_t b) {
  asm volatile("{\n.reg .b64 v;\nmov.b64 v, {%1, %2};\nst.relaxed.gpu.global.b64 [%0], v;\n}\n" :: "l"(p), "r"(a), "r"(b) : "memory");
}
__device__ __forceinline__ void st_b128(uint4* p, uint32_t a, uint32_t b, uint32_t c, uint32_t d) {
  asm volatile("{\n.reg .b128 v;\nmov.b128 v, {%1, %2, %3, %4};\nst.relaxed.gpu.global.b128 [%0], v;\n}\n" :: "l"(p), "r"(a), "r"(b), "r"(c), "r"(d) : "memory");
}
__device__ __forceinline__ uint4 ld_b128(const uint4* p) {
  uint4 v;
  asm volatile("{\n.reg .b128 v;\nld.relaxed.gpu.global.b128 v, [%4];\nmov.b128 {%0, %1, %2, %3}, v;\n}\n" : "=r"(v.x), "=r"(v.y), "=r"(v.z), "=r"(v.w) : "l"(p) : "memory");
  return v;
}

constexpr float LOG2E = 1.4426950408889634f;

struct Params {
  const __nv_bfloat16* x0;
  const __nv_bfloat16* wA_qkv;
  const __nv_bfloat16* wA_o;
  const __nv_bfloat16* wB_qkv;
  const __nv_bfloat16* wB_phi;
  const __nv_bfloat16* wB_o;
  __nv_bfloat16* out;
};

#define ACC_DEF(d, n) _Pragma("unroll") for (int i_ = 0; i_ < (n); i_++) asm volatile("" : "=f"(d[i_]))
#define ACC_FENCE(d, n) _Pragma("unroll") for (int i_ = 0; i_ < (n); i_++) asm volatile("" : "+f"(d[i_]) :: "memory")
#define PIN(a, n) _Pragma("unroll") for (int i_ = 0; i_ < (n); i_++) asm volatile("" : "+f"((a)[i_]))
#define PINU(a, n) _Pragma("unroll") for (int i_ = 0; i_ < (n); i_++) asm volatile("" : "+r"((a)[i_]))

#define V_ADDR(p0) uint32_t va_[2] = {(p0) + (srowoff >> 1) + (lhi ^ lsw2), (p0) + (srowoff >> 1) + ((32 + lhi) ^ lsw2)}
#define STAGE_V(acc) { \
    _Pragma("unroll") for (int j_ = 0; j_ < 4; j_++) { \
      const float* a_ = (acc) + j_ * 8; \
      stsm_x4(va_[j_ & 1] + (j_ >> 1) * 8192, \
              pack_bf16(rs0 * a_[0], rs0 * a_[1]), pack_bf16(rs1 * a_[2], rs1 * a_[3]), pack_bf16(rs0 * a_[4], rs0 * a_[5]), pack_bf16(rs1 * a_[6], rs1 * a_[7])); } }
#define FRAG(dst, acc, TR, grp) { \
    _Pragma("unroll") for (int i_ = 0; i_ < 16; i_++) { \
      const float r_ = (i_ & 1) ? rs1 : rs0; \
      const uint32_t w_ = pack_bf16(r_ * (acc)[2 * i_], r_ * (acc)[2 * i_ + 1]); \
      if (TR) (dst)[i_] = movm_t(w_); else (dst)[(i_ & 12) + (i_ & 1) * 2 + ((i_ >> 1) & 1)] = w_; } \
    if (warp == 7 && mm < 15) { \
      _Pragma("unroll") for (int j_ = 0; j_ < 4; j_++) \
        st_b128(g_halo + (size_t)(mm * 8 + jj) * 512 + ((grp) * 4 + j_) * 32 + lane, ((dst)[j_ * 4] & ~1u) | H_BIT(l), (dst)[j_ * 4 + 1], (dst)[j_ * 4 + 2], (dst)[j_ * 4 + 3]); } \
    PINU(dst, 16); }
#define FRAG_PUT(src, slot) if (warp < 7) { _Pragma("unroll") for (int j_ = 0; j_ < 4; j_++) \
      sts128(sbase + (slot) * SLOT + 2048 + warp * 2048 + j_ * 512 + lane * 16, (src)[j_ * 4], (src)[j_ * 4 + 1], (src)[j_ * 4 + 2], (src)[j_ * 4 + 3]); }
#define FRAG_GET(dst, slot) { _Pragma("unroll") for (int j_ = 0; j_ < 4; j_++) \
      asm volatile("ld.shared.v4.u32 {%0, %1, %2, %3}, [%4];" : "=r"((dst)[j_ * 4]), "=r"((dst)[j_ * 4 + 1]), "=r"((dst)[j_ * 4 + 2]), "=r"((dst)[j_ * 4 + 3]) \
                   : "r"(sbase + (slot) * SLOT + warp * 2048 + j_ * 512 + lane * 16) : "memory"); }
#define RW(j) (((j) >> 1) * 4 + ((j) & 1))
template <int POS> __device__ __forceinline__ float exps16_(float* o, const float* p) {
  float s[4];
#pragma unroll
  for (int j = 0; j < 16; j++) { o[j] = ex2(POS ? p[RW(j)] : -p[RW(j)]); if (j < 4) s[j] = o[j]; else s[j & 3] += o[j]; }
  const float r = (s[0] + s[1]) + (s[2] + s[3]);
  return r + __shfl_xor_sync(0xffffffffu, r, 1);
}
template <int POS> __device__ __forceinline__ void exps16_fix(float* o, const float* p, float& sum) {
  if (__builtin_expect(__any_sync(0xffffffffu, !(sum > SUMLO && sum < SUMHI)), 0)) {
    float m = p[0], q[32];
#pragma unroll
    for (int j = 1; j < 16; j++) m = POS ? fmaxf(m, p[RW(j)]) : fminf(m, p[RW(j)]);
    const float x = __shfl_xor_sync(0xffffffffu, m, 1);
    m = POS ? fmaxf(m, x) : fminf(m, x);
#pragma unroll
    for (int j = 0; j < 16; j++) q[RW(j)] = p[RW(j)] - m;
    sum = exps16_<POS>(o, q);
  }
}
__device__ __forceinline__ void store16(const float* e, float sum, uint32_t dst, uint32_t dsw, int c0) {
  const float inv = rcp_fast(sum);
#pragma unroll
  for (int j = 0; j < 2; j++)
    sts128(dst + (((c0 + j) << 4) ^ dsw), pack_bf16(e[j * 8] * inv, e[j * 8 + 1] * inv), pack_bf16(e[j * 8 + 2] * inv, e[j * 8 + 3] * inv),
           pack_bf16(e[j * 8 + 4] * inv, e[j * 8 + 5] * inv), pack_bf16(e[j * 8 + 6] * inv, e[j * 8 + 7] * inv));
}
template <int POS> __device__ __forceinline__ void expp16(uint32_t* o, float* p) {
  {
#pragma unroll
    for (int r = 0; r < 4; r += 2) {
      float m = p[r];
#pragma unroll
      for (int j = 1; j < 8; j++) m = POS ? fmaxf(m, p[r + RW(j)]) : fminf(m, p[r + RW(j)]);
#pragma unroll
      for (int s = 1; s <= 2; s <<= 1) { const float x = __shfl_xor_sync(0xffffffffu, m, s); m = POS ? fmaxf(m, x) : fminf(m, x); }
#pragma unroll
      for (int j = 0; j < 8; j++) p[r + RW(j)] -= m;
    }
  }
#pragma unroll
  for (int j = 0; j < 8; j++) o[j] = pack_bf16(ex2(POS ? p[2 * j] : -p[2 * j]), ex2(POS ? p[2 * j + 1] : -p[2 * j + 1]));
}
__device__ __forceinline__ void scale32(float* o, const float* p, float c0, float c1) {
#pragma unroll
  for (int i = 0; i < 32; i++) asm volatile("mul.f32 %0, %1, %2;" : "=f"(o[i]) : "f"(p[i]), "f"((i & 2) ? c1 : c0));
}
__device__ __forceinline__ bool any_big(const float* p) {
  float m[4];
#pragma unroll
  for (int i = 0; i < 32; i++) m[i >> 3] = (i & 7) ? fmaf(p[i], p[i], m[i >> 3]) : p[i] * p[i];
  return __any_sync(0xffffffffu, !(fmaxf(fmaxf(m[0], m[1]), fmaxf(m[2], m[3])) < BIGLIM));
}
__device__ __forceinline__ void phiq_a(float* p, bool big) {
  if (__builtin_expect(!big, 1)) {
#pragma unroll
    for (int j = 0; j < 16; j++) p[j] = ex2(p[j]);
  }
}
template <int NEXT> __device__ __forceinline__ void phiq_b(uint32_t* o, float* p, bool big) {
  if (__builtin_expect(big, 0)) {
    expp16<0>(o, p); expp16<1>(o + 8, p);
  } else {
    if (NEXT) phiq_a(p + 16, false);
#pragma unroll
    for (int j = 0; j < 4; j++) {
      const float a = p[4 * j], b = p[4 * j + 1], c = p[4 * j + 2], d = p[4 * j + 3];
      const float ab = a * b, cd = c * d, r = rcp_fast(ab * cd), x = r * cd, y = r * ab;
      o[2 * j] = pack_bf16(x * b, x * a); o[2 * j + 1] = pack_bf16(y * d, y * c);
      o[8 + 2 * j] = pack_bf16(a, b); o[9 + 2 * j] = pack_bf16(c, d);
    }
  }
}
#define SCHED_FENCE() asm volatile("pmevent 0;" ::: "memory")

__global__ void __cluster_dims__(2, 1, 1) __launch_bounds__(384, 1)
mega_kernel(const __grid_constant__ CUtensorMap tm_x0, const __grid_constant__ CUtensorMap tm_xo, const __grid_constant__ CUtensorMap tm_os,
            const __grid_constant__ CUtensorMap tm_o, const __grid_constant__ CUtensorMap tm_wf,
            const __grid_constant__ CUtensorMap tm_wqA, const __grid_constant__ CUtensorMap tm_wqB,
            const __grid_constant__ CUtensorMap tm_woA, const __grid_constant__ CUtensorMap tm_woB,
            const __grid_constant__ CUtensorMap tm_phi, const Params prm) {
  extern __shared__ __align__(1024) uint8_t smem_raw[];
  const uint32_t sbase = smem_u32(smem_raw);
  const uint32_t bar_full = sbase + OFF_BAR;
  const uint32_t bar_done = bar_full + 384;
  const uint32_t bar_stat = bar_full + 768, bar_stat2 = bar_full + 776, bar_epi = bar_full + 784, bar_phi = bar_full + 936  , bar_halo = bar_full + 904  ;
  const uint32_t bar_xr = bar_full + 800, bar_lx = bar_full + 808, bar_stg = bar_full + 832;
  const uint32_t bar_chk = bar_full + 848;

  const int warp = __shfl_sync(0xffffffffu, threadIdx.x >> 5, 0), lane = threadIdx.x & 31;
  const uint32_t bar_kx = sbase + OFF_ID + 384 + warp * 8;
  uint32_t rank;
  asm volatile("mov.u32 %0, %%cluster_ctarank;" : "=r"(rank));
  const int aux = (int)blockIdx.x - NMAIN, tp = (int)(blockIdx.x >> 1) - 4;
  const int gp = tp < 0 ? 0 : (tp < 32 ? tp & 7 : 1 + (tp - 32) % 7), me = tp < 0 ? tp + 8 : (tp < 32 ? tp >> 3 : 4 + (tp - 32) / 7);
  const int jj = me, cc = gp;
  const int cta = aux >= 0 ? -1 : (cc * 8 + jj) * 2 + (int)rank;
  const int mm = cc * 2 + (int)rank;

#define LOAD_EPOCH() const unsigned epoch = ld_relaxed(&g_flags.epoch.v), ep1 = epoch + 1; (void)epoch
  int budget = 1 << 22;

  if (cta >= 0) {
    if (warp >= 8 + CPA && warp < 8 + EARLY && elect_one()) {
      const int u = warp - 8;
      const uint32_t fb = bar_full + u * 8;
      mbar_init(fb, 1);
      asm volatile("fence.mbarrier_init.release.cluster;" ::: "memory");
      fence_proxy_async_smem();
      mbar_expect_tx(fb, UPS(u) ? QST : QST + SLOT);
      if (u) __nanosleep(UPS(u) ? STAG1 : STAG2);
      if (!UPS(u)) tma_load_2d(sbase + OFF_S + USL(u) * SLOT, &tm_x0, fb, jj * 128 + USL(u) * 64, mm * 128);
#pragma unroll
      for (int i = 0; i < 6; i++) tma_load_2d(sbase + u * QST + i * 4096, &tm_wqA, fb, jj * 128 + UPS(u) * 64 + (i >> 1) * 1024, jj * 128 + USL(u) * 64 + (i & 1) * 32);
      if (u == 0) PROFT(472);
    }
    __syncwarp();
    {
      const int tx = threadIdx.x;
      const __nv_bfloat16* pf = (tx < 128) ? prm.x0 + (size_t)(mm * 128 + tx) * D_MODEL + jj * 128
                                           : prm.wA_qkv + (size_t)(jj * 128 + (tx & 63)) * 3072 + ((tx - 128) >> 6) * 1024 + jj * 128 + rank * 64;
      if (tx < 320) { if (PF0 && !CPA) asm volatile("prefetch.global.L2 [%0];" :: "l"(pf)); }
      if (PFW && tx < 24 * PFW) {
        const int q = tx % 24;
        asm volatile("prefetch.global.L2 [%0];" :: "l"(prm.wA_qkv + (size_t)(kslice(jj, 2 + tx / 24) * 64 + mm * 4 + q / 6) * 3072 + (q % 6 >> 1) * 1024 + jj * 128 + (q & 1) * 64));
      }
      if (tx == 320) prefetch_tmap(&tm_x0);
      else if (tx == 352) prefetch_tmap(&tm_wqA);
      else if (tx == 383) asm volatile("prefetch.global.L2 [%0];" :: "l"(&g_flags.epoch.v));
    }
    if (elect_one()) {
#pragma unroll
      for (int i = 0; i < 4; i++) {
        const int u = warp * 4 + i;
        if (u >= EARLY || u < CPA) mbar_init(bar_full + u * 8, ((u >= 4 && u < 11) || (u > 32 && u != 40)) ? 2 : 1); mbar_init(bar_done + u * 8, 16);
      }
      mbar_init(bar_stat + warp * 16, 0x111111181182ull >> (4 * warp) & 15);
      mbar_init(bar_stat + warp * 16 + 8, 0x111111121811ull >> (4 * warp) & 15);
      mbar_init(bar_chk + 112 + (warp & 7) * 8, 1);
      if (PAIR) mbar_init(bar_kx, 1);
      asm volatile("fence.mbarrier_init.release.cluster;" ::: "memory");
    }
    __syncwarp();
    __syncthreads();
    asm volatile("barrier.cluster.arrive.relaxed.aligned;" ::: "memory");
  }

  if (cta < 0) {
    LOAD_EPOCH();
    const uint32_t buf = sbase + warp * SLOT, bar = sbase + OFF_BAR + warp * 16;
    const uint32_t lsw = (lane & 7) << 4, lhi = (lane >> 4) << 4, lrow = (lane & 15) * 128;
    const bool el = elect_one();
    if (el) {
      mbar_init(bar, 1); mbar_init(bar + 8, 1);
      asm volatile("fence.mbarrier_init.release.cluster;" ::: "memory");
    }
#pragma unroll 1
    for (int rd = 0; rd < (NLAYERS > 1 ? 5 : 2); rd++) {
      if (rd >= 2 && warp >= 8) break;
      const int tk = rd < 2 ? aux * 12 + warp : aux * 8 + warp;
      const int half = tk & 1;
      const int blk = rd < 2 ? (tk >> 1) * 2 + rd : (4 - rd) * 16 + (tk >> 1);
      const CUtensorMap* tm = rd < 2 ? &tm_wqA : (rd == 2 ? &tm_wqB : &tm_wf);
      const int j0 = (blk & 15) >> 1;
#define AUX_LOAD(n) { const uint32_t d_ = buf + ((n) & 1) * 8192, b_ = bar + ((n) & 1) * 8; const int r_ = kslice(j0, 2 * (n) + half) * 64; \
        mbar_expect_tx(b_, 8192); tma_load_2d(d_, tm, b_, blk * 64, r_); tma_load_2d(d_ + 4096, tm, b_, blk * 64, r_ + 32); }
      if (el) {
        if (rd == 3) { wait_flag(&g_flags.wfready[j0].v, ep1 * 16); fence_proxy_async_global(); }
        AUX_LOAD(0); AUX_LOAD(1);
      }
      __syncwarp();
      float cs[8][4];
#pragma unroll
      for (int i = 0; i < 8; i++) cs[i][0] = cs[i][1] = cs[i][2] = cs[i][3] = 0.f;
#pragma unroll 1
      for (int n = 0; n < 8; n++) {
        const uint32_t tb = buf + (n & 1) * 8192 + lrow;
        mbar_wait(bar + (n & 1) * 8, (n >> 1) & 1);
#pragma unroll
        for (int i = 0; i < 16; i++) {
          uint32_t b0, b1, b2, b3;
          ldsm_x4_t(tb + (i >> 2) * 2048 + (((i & 3) * 32 + lhi) ^ lsw), b0, b1, b2, b3);
          mma_bf16(cs[2 * (i & 3)], 0x3F803F80u, 0x3F803F80u, 0x3F803F80u, 0x3F803F80u, b0, b1);
          mma_bf16(cs[2 * (i & 3) + 1], 0x3F803F80u, 0x3F803F80u, 0x3F803F80u, 0x3F803F80u, b2, b3);
        }
        __syncwarp();
        if (el && n < 6) AUX_LOAD(n + 2);
        __syncwarp();
      }
      if (lane < 4) {
#pragma unroll
        for (int i = 0; i < 8; i++) st_b64(&g_colsum[rd >= 2][blk * 32 + i * 4 + lane][half], __float_as_uint(cs[i][0]), (__float_as_uint(cs[i][1]) & ~3u) | (ep1 & 3));
      }
      __syncwarp();
    }
  } else if (warp >= 8) {
    asm volatile("setmaxnreg.dec.sync.aligned.u32 40;");
    if (warp == 8) {
      const bool el = elect_one();
      cluster_wait();
      if (el) {
#pragma unroll 1
        for (int l = 0; l < NLAYERS; l++) {
          const uint32_t par = l & 1;
          const CUtensorMap* tqk = par ? &tm_wf : &tm_wqA;
          const CUtensorMap* tv = par ? &tm_wqB : &tm_wqA;
          const CUtensorMap* two = par ? &tm_woB : &tm_woA;
          if (l == 1) { LOAD_EPOCH(); wait_flag(&g_flags.wfready[jj].v, ep1 * 16); fence_proxy_async_global(); }
#pragma unroll 1
          for (int u = l ? 0 : EARLY; u < 32; u++) {
            if (u >= 4) mbar_wait_sl(bar_done + (u - 4) * 8, par);
            else if (l) mbar_wait_sl(bar_done + (43 + u + (u >> 1)) * 8, par ^ 1);
            else if (!W23) mbar_wait_sl(bar_full, 0);
            const uint32_t fb = bar_full + u * 8;
            const bool res = u < 11 || (u >= 18 && u < 22);
            mbar_expect_tx(fb, res ? QST : QST + SLOT);
            const int row = kslice(jj, u < 4 ? USL(u) : (u < 18 ? u - 2 : (u < 22 ? u - 6 : u - 20))) * 64 + (int)rank * 32;
            const int ps = u < 4 ? UPS(u) : (u >= 18), col = jj * 128 + ps * 64;
            const int c0 = par ? jj * 128 + (ps ? 0 : 1024) : col;
            const uint32_t dst = sbase + (u & 3) * QST + rank * 4096;
            tma_load_2d_mc(dst, tqk, fb, c0, row);
            tma_load_2d_mc(dst + 8192, tqk, fb, c0 + (par ? 64 : 1024), row);
            tma_load_2d_mc(dst + 16384, tv, fb, col + 2048, row);
            if (l == PRL && u >= PRU && u < PRU + 4) PROFT(473 + u - PRU);
          }
#pragma unroll 1
          for (int s = 0; s < 16; s++) {
            if (s < 5) { if (s != 2 && s != 4) mbar_wait_sl(bar_done + (28 + s) * 8, par); }
            else if (s != 14) mbar_wait_sl(bar_done + (27 + s - (s == 15)) * 8, par);
            const uint32_t fb = bar_full + (32 + s) * 8;
            mbar_expect_tx(fb, SLOT);
            tma_load_2d_mc(sbase + rank * 8192 + (uint32_t)((WO_BSLOT >> (4 * s)) & 15) * SLOT, two, fb, jj * 128 + (int)rank * 64, wslice(jj, s) * 64);
            const int ts = s + par;
            if (s >= 5 && ts < 8) {
              mbar_expect_tx(bar_chk - 8 + ts * 8, SLOT);
              tma_load_2d(sbase + (uint32_t)((WO_ASLOT(par) >> (4 * ts)) & 15) * SLOT, &tm_o, bar_chk - 8 + ts * 8, wslice(jj, ts) * 64, mm * 128);
            }
          }
        }
      }
      __syncwarp();
    } else if (warp == 9) {
      const bool el = elect_one();
      LOAD_EPOCH();
#pragma unroll 1
      for (int lp = 0; lp < 4 * NLAYERS; lp++) {
        const int l = lp >> 2, ph = lp & 3;
        if (ph == 3) continue;
        const uint32_t par = l & 1;
        const unsigned* pp = reinterpret_cast<const unsigned*>(g_obuf + (ph >> 1) * 64 + (size_t)(mm * 128 + (ph ? 0 : S_LEN) + ((lane & 7) | PROWS) * 16 + (jj & 1) * 8) * D_MODEL +
                                                               (jj >> 1) * 16 + srcb(jj, lane >> 3) * 128);
        const CUtensorMap* tm = lp ? &tm_o : &tm_x0;
        const int row = mm * 128 + ((ph || !l) ? 0 : S_LEN);
        const uint32_t bit = ph ? O_BIT(l) : X_BIT(l - 1);
        const uint32_t slots = ph ? (uint32_t)(WO_ASLOT(par) >> (ph * 32 - 28)) : 0x8769876u;
        const unsigned long long fr = ph == 0 ? XPACE : ph == 1 ? (par ? FRB : 0x35351F1Eull) : (par ? 0x27262524232232ull : 0x27262524233232ull);
        uint32_t no = (lp == 0 || (lp & 7) == 1) ? 0 : (ph == 1 ? NOB : (ph ? NO1 : NOX)), v0 = 0, v1 = 0;
        if (lp || !AX) mbar_wait_sl(ph ? bar_done + ((uint32_t)fr & 63) * 8 : (l ? bar_done + 47 * 8 : bar_full), ph ? par : (l ? par ^ 1 : 0));
        if (el && ph) PROFT(324 + l * 16 + ph);
        __syncwarp();
        if (no && (ph == 1 ? SPD1 : (ph ? SPD2 : SPD0))) __nanosleep(ph == 1 ? SPD1 : (ph ? SPD2 : SPD0));
        if (no) { v0 = ld_relaxed(pp); __nanosleep(POLLGAP); v1 = ld_relaxed(pp); }
#pragma unroll 1
        for (int i = 0; i < (ph == 1 ? 4 + par : 7); i++, no >>= 8) {
#pragma unroll 1
          for (int it = 0; (no & 0xFF) && it < (1 << 18); it++) {
            no &= __ballot_sync(0xffffffffu, (v0 ^ bit) & 1) >> (8 * i);
            if (no) v0 = ld_relaxed(pp);
            if (!(no & 0xFF)) break;
            no &= __ballot_sync(0xffffffffu, (v1 ^ bit) & 1) >> (8 * i);
            if (no) v1 = ld_relaxed(pp);
          }
          if (ph || i >= XP0) mbar_wait_sl(bar_done + ((uint32_t)(fr >> (8 * i)) & 63) * 8, par);
          if (el) {
            if (i == 0) PROFT(320 + l * 16 + ph);
            const uint32_t cb = (lp ? bar_chk + (ph >> 1) * 112 : bar_full + 32) + i * 8;
            mbar_expect_tx(cb, SLOT);
            tma_load_2d(sbase + ((slots >> (4 * i)) & 15) * SLOT, tm, cb, srcb(jj, i) * 128 + (ph >> 1) * 64, row);
          }
          __syncwarp();
        }
        if (ph == 0 && el) {
          if (l) { wait_flag(&g_flags.xready[l][mm].v, ep1 * 8); fence_proxy_async_global(); }
#pragma unroll 1
          for (int u = 11; u < 34; u++) {
            if (u == 18) u = 22;
            mbar_wait_sl(bar_done + (u - 4) * 8, par);
            if (u == 32) mbar_expect_tx(bar_xr, 2 * SLOT);
            tma_load_2d(sbase + OFF_RA + (u & 3) * SLOT, tm, u < 32 ? bar_full + u * 8 : bar_xr, kslice(jj, u < 18 ? u - 2 : (u < 32 ? u - 20 : u - 32)) * 64, row);
          }
        }
        __syncwarp();
      }
      if (el && atomicAdd(&g_flags.done.v, 1) == ep1 * NMAIN - 1) asm volatile("st.relaxed.gpu.global.u32 [%0], %1;" :: "l"(&g_flags.epoch.v), "r"(ep1) : "memory");
      __syncwarp();
      cluster_wait();
    } else {
      const int hw = warp - 10;
      LOAD_EPOCH();
      const bool el = elect_one();
      cluster_wait();
      if (hw == 0) {
        mbar_wait_sl(bar_full + 8 + 8 * ORD, 0);
        if (lane < 7) prefetch_tmap(lane == 0 ? &tm_os : lane == 1 ? &tm_o : lane == 2 ? &tm_wf : lane == 3 ? &tm_wqB : lane == 4 ? &tm_woA : lane == 5 ? &tm_woB : &tm_phi);
#pragma unroll 1
        for (int i = 0; i < (NLAYERS > 1 ? 9 : 0); i++) {
          if (i == 0 || i == 5) mbar_wait_sl(bar_done + (i ? FD1 : FD0) * 8, 0);
          if (el) {
            if (i == 0) { mbar_expect_tx(bar_phi, 2 * SLOT + 8192); tma_load_2d(sbase + OFF_PHI, &tm_phi, bar_phi, 0, jj * 128); }
            else tma_load_2d(sbase + (i > 4 ? 10 : 12) * SLOT - 4096 + i * 4096, &tm_wqB, bar_phi, (i > 4 ? 896 : 0) + jj * 128 + ((i - 1) >> 1) * 64, mm * 64 + (~i & 1) * 32);
          }
          __syncwarp();
          __nanosleep(PFGAP);
        }
      } else {
        if (XMMA && lane < 24) {
          const uint32_t one = (lane & 8) ? 0u : 0x3F80u << ((lane & 1) * 16), w = (lane >> 1) & 3;
          sts128(sbase + OFF_ID + lane * 16, w == 0 ? one : 0u, w == 1 ? one : 0u, w == 2 ? one : 0u, w == 3 ? one : 0u);
        }
#pragma unroll 1
        for (int b = 0; b < 2; b++) {
          float4* z = reinterpret_cast<float4*>(g_kv[b] + (jj * 4) * KVH + mm * (4 * KVH / 16)) + lane;
#pragma unroll
          for (int i = 0; i < 6; i++) z[i * 32] = make_float4(0.f, 0.f, 0.f, 0.f);
        }
#pragma unroll 1
        for (int i = 0; i < 16; i++) {
          const int b = i >> 2;
          const uint32_t v = (b == 0 ? O_BIT(0) : b == 1 ? X_BIT(0) : H_BIT(0)) + 1;
          uint4* p = b < 2 ? reinterpret_cast<uint4*>(g_obuf + (size_t)(b * S_LEN + mm * 128 + (i & 3) * 32 + (lane >> 3) * 8) * D_MODEL + jj * 128 + (b ? 0 : 64)) + (lane & 7)
                           : g_halo + (size_t)(mm * 8 + jj) * 512 + i * 32 + lane;
          *p = make_uint4(v, v, v, v);
        }
        fence_proxy_async_global();
      }
      __syncwarp();
      uint32_t chkp = 0;
#pragma unroll 1
      for (int lp = hw; lp < 8 * NLAYERS; lp++) {
        const int l = lp >> 3, tk = lp & 7, ph = tk ? 2 - hw : 0;
        const uint32_t par = l & 1;
        int lane; asm volatile("mov.u32 %0, %%laneid;" : "=r"(lane));
        if (tk == 5 || (hw && tk == 0)) {
          const uint32_t bit = ph ? O_BIT(l) : X_BIT(l - 1);
          uint32_t slots = ph ? (uint32_t)(WO_ASLOT(par) >> (ph * 32 - 28)) : 0x8769876u;
          const uint32_t a0 = sbase + (lane & 7) * 126 + lane * 4 + (lane & 1) * 14;
#pragma unroll 1
          for (int c = 0; c < 7; c++, slots >>= 4) {
            const uint32_t cb = bar_chk + 112 - hw * 112 + c * 8;
#pragma unroll 1
            for (int it = 0; it < (1 << 12); it++) {
              mbar_wait_sl(cb, (chkp >> c) & 1);
              chkp ^= 1u << c;
              if (el && c == 0) PROFT(ph == 1 ? 480 + l * 2 : 488 + l * 2 + (ph >> 1));
              uint32_t bad;
              asm volatile("{\n.reg .b32 w<16>;\n"
                           "ld.shared.u32 w0, [%1 + 0];\n"
                           "ld.shared.u32 w1, [%1 + 1024];\n"
                           "ld.shared.u32 w2, [%1 + 2048];\n"
                           "ld.shared.u32 w3, [%1 + 3072];\n"
                           "ld.shared.u32 w4, [%1 + 4096];\n"
                           "ld.shared.u32 w5, [%1 + 5120];\n"
                           "ld.shared.u32 w6, [%1 + 6144];\n"
                           "ld.shared.u32 w7, [%1 + 7168];\n"
                           "ld.shared.u32 w8, [%1 + 8192];\n"
                           "ld.shared.u32 w9, [%1 + 9216];\n"
                           "ld.shared.u32 w10, [%1 + 10240];\n"
                           "ld.shared.u32 w11, [%1 + 11264];\n"
                           "ld.shared.u32 w12, [%1 + 12288];\n"
                           "ld.shared.u32 w13, [%1 + 13312];\n"
                           "ld.shared.u32 w14, [%1 + 14336];\n"
                           "ld.shared.u32 w15, [%1 + 15360];\n"
                           "lop3.b32 w0, w0, w1, %2, 0x7E;\n"
                           "lop3.b32 w2, w2, w3, %2, 0x7E;\n"
                           "lop3.b32 w4, w4, w5, %2, 0x7E;\n"
                           "lop3.b32 w6, w6, w7, %2, 0x7E;\n"
                           "lop3.b32 w8, w8, w9, %2, 0x7E;\n"
                           "lop3.b32 w10, w10, w11, %2, 0x7E;\n"
                           "lop3.b32 w12, w12, w13, %2, 0x7E;\n"
                           "lop3.b32 w14, w14, w15, %2, 0x7E;\n"
                           "lop3.b32 w0, w0, w2, w4, 0xFE;\nlop3.b32 w6, w6, w8, w10, 0xFE;\nlop3.b32 w0, w0, w12, w14, 0xFE;\nlop3.b32 %0, w0, w6, 1, 0xA8;\n}\n"
                           : "=r"(bad) : "r"(a0 + (slots & 15) * SLOT), "r"(bit) : "memory");
              if (__all_sync(0xffffffffu, bad == 0)) break;
              if (el) {
                fence_proxy_async_smem();
                mbar_expect_tx(cb, SLOT);
                tma_load_2d(sbase + (slots & 15) * SLOT, &tm_o, cb, srcb(jj, c) * 128 + (ph >> 1) * 64, mm * 128 + (ph ? 0 : S_LEN));
                RETRY_COUNT();
              }
              __syncwarp();
            }
            if (el) { mbar_arrive_local(bar_full + (c + (ph ? 25 + ph * 8 : 4)) * 8); if (lp == PRL * 8 && c == 0) PROFT(477); }
            __syncwarp();
          }
        } else if (hw && (tk & 5) == 1) {
          {
            const int hp = tk >> 1;
            const uint4* src = reinterpret_cast<const uint4*>(g_colsum[par][jj * 64 + hp * 32 + lane]);
            uint32_t bad;
            int it = 0;
            float c[6];
            do {
              bad = 0;
#pragma unroll
              for (int p = 0; p < 3; p++) {
                const uint4 v = ld_ll(src + ((par && p < 2) ? (hp ? -32 : 512) + p * 32 : p * 512));
                bad |= (v.y ^ ep1) | (v.w ^ ep1);
                c[2 * p] = __uint_as_float(v.x) + __uint_as_float(v.z); c[2 * p + 1] = __uint_as_float(v.y) + __uint_as_float(v.w);
              }
              bad &= 3;
              if (bad) __nanosleep(300);
            } while (bad && ++it < (1 << 16));
#pragma unroll
            for (int p = 0; p < 6; p++) {
              uint32_t h, m, lo;
              split3(c[p], h, m, lo);
              sts128(sbase + OFF_LNB + hp * 4096 + (p >> 1) * 1024 + lane * 32 + (p & 1) * 16, h | (m << 16), h | (lo << 16), h | (m << 16), lo | (m << 16));
            }
            fence_proxy_async_smem();
            __syncwarp();
            if (el) { mbar_arrive_local(hp ? bar_stat2 : bar_stat); if (hp == 0) PROFT(324 + l * 16); }
            __syncwarp();
          }
        } else if (tk == 0) {
          mbar_wait_sl(bar_done + 24, par);
          const uint4* sp = reinterpret_cast<const uint4*>(g_stats + (size_t)(mm * 128) * 8) + lane;
#pragma unroll 1
          for (int hf = 0; hf < 4; hf++) {
            uint4 v[4];
            uint32_t bad;
            int it = 0;
            do {
              bad = 0;
#pragma unroll
              for (int i = 0; i < 4; i++) { v[i] = ld_ll(sp + (hf * 4 + i) * 32); bad |= (v[i].y ^ STAT_TAG(l)) | (v[i].w ^ STAT_TAG(l)); }
              bad &= 3;
              if (bad) __nanosleep(200);
            } while (bad && ++it < (1 << 16));
            __syncwarp();
            float mean = 0.f, m2 = 0.f;
#pragma unroll
            for (int i = 0; i < 4; i++) {
              float a = __uint_as_float(v[i].x) + __uint_as_float(v[i].z);
              a += __shfl_xor_sync(0xffffffffu, a, 1); a += __shfl_xor_sync(0xffffffffu, a, 2);
              a *= 0.125f;
              const float e0 = __uint_as_float(v[i].x) - a, e1 = __uint_as_float(v[i].z) - a;
              float q = fmaf(fmaf(e0, e0, e1 * e1), 128.f, __uint_as_float(v[i].y) + __uint_as_float(v[i].w));
              q += __shfl_xor_sync(0xffffffffu, q, 1); q += __shfl_xor_sync(0xffffffffu, q, 2);
              if ((lane & 3) == i) { mean = a; m2 = q; }
            }
            const uint32_t row = hf * 32 + (lane & 3) * 8 + (lane >> 2);
            uint32_t h, m, lo;
            split3(-0.5f * mean, h, m, lo);
            sts128(sbase + OFF_LNA + row * 16, h | (h << 16), m | (h << 16), lo | (m << 16), m | (lo << 16));
            sts32f(sbase + OFF_ST + row * 4, rsqrtf(m2 * (1.f / 1024.f) + 1e-5f));
          }
          fence_proxy_async_smem();
          __syncwarp();
          if (el) { mbar_arrive_local(bar_stat); PROFT(323 + l * 16); }
          __syncwarp();
#pragma unroll 1
          for (int i = 0; i < 8 - 4 * l; i++) {
            asm volatile("prefetch.global.L2 [%0];" :: "l"(i < 4 ? (l ? prm.wB_o : prm.wA_o) + (size_t)cta * 8192 + i * 2048 + lane * 64
                                                                 : prm.wB_qkv + (size_t)(cta * 8 + (i - 4) * 2 + (lane >> 4)) * 3072 + 2048 + (lane & 15) * 64));
            __nanosleep(PFGAP);
          }
        } else if (lp == 3) {
#pragma unroll 1
          for (int c = 0; c < (NLAYERS > 1 ? 8 : 0); c++) {
            if (!(c & 3)) asm volatile("bar.sync %0, 288;" :: "r"(BAR_WF + (c >> 2)) : "memory");
            if (el) {
              tma_store_2d(&tm_wf, sbase + 11 * SLOT + c * 4096, (c < 4 ? 1024 : -128) + jj * 128 + (c >> 1) * 64, mm * 64 + (c & 1) * 32);
              if ((c & 3) == 3) {
                asm volatile("cp.async.bulk.commit_group;\ncp.async.bulk.wait_group.read 0;" ::: "memory");
                mbar_arrive_local(bar_phi + (c >> 2) * 8);
              } else __nanosleep(WFGAP);
            }
            __syncwarp();
          }
          if (el) { bulk_commit_wait(); signal_release(&g_flags.wfready[jj].v); PROFT(335); }
          __syncwarp();
        } else if (tk == 2 || tk == 4) {
          if (par) continue;
          const int i = tk >> 2;
          mbar_wait_sl(bar_done + (i ? HW1 : (hw ? 19 : HW0)) * 8, 0);
          if (HDEL && i) __nanosleep(HDEL + hw * HDEL1);
          const uint4* src = g_halo + (size_t)(mm * 8 + jj - 8) * 512 + i * 256 + hw * 128 + lane;
          uint4 v[4];
          int it = 0;
          bool ok;
          do {
#pragma unroll
            for (int j = 0; j < 4; j++) v[j] = mm ? ld_b128(src + j * 32) : make_uint4(H_BIT(l), 0, 0, 0);
            ok = __all_sync(0xffffffffu, (((v[0].x ^ H_BIT(l)) | (v[1].x ^ H_BIT(l)) | (v[2].x ^ H_BIT(l)) | (v[3].x ^ H_BIT(l))) & 1) == 0);
            if (HSL && !ok) __nanosleep(HSL);
          } while (!ok && ++it < (1 << 16));
          if (lp + hw == 3 && NLAYERS > 1) mbar_wait_sl(bar_phi, 1);
#pragma unroll
          for (int j = 0; j < 4; j++) sts128(sbase + OFF_S + hw * SLOT + j * 512 + lane * 16, v[j].x, v[j].y, v[j].z, v[j].w);
          __syncwarp();
          if (el) { mbar_arrive_local(bar_halo + hw * 8); PROFT(331 + l * 16 + i * 2 + hw); }
          __syncwarp();
        } else if (tk == 6 && hw == 0 && l < NLAYERS - 1) {
          bar_sync<BAR_X1, 288>();
          if (el) {
            PROFT(328 + l * 16);
            mbar_wait_sl(bar_full + XD * 8, par ^ 1);
            tma_store_2d(&tm_o, sbase + 11 * SLOT, jj * 128 + 64, mm * 128 + S_LEN);
            bulk_commit_wait();
            signal_release(&g_flags.xready[l + 1][mm].v);
            PROFT(330 + l * 16);
          }
          __syncwarp();
        }
      }
    }
    cluster_sync();
  } else {
    asm volatile("setmaxnreg.inc.sync.aligned.u32 232;");
    const int wg = warp >> 2;
    const int r0 = warp * 16;
    const uint32_t pK = sbase + OFF_S, pV = sbase + OFF_S + SLOT;
#define PMASKS(on, bit) const uint32_t pm0 = ((on) && t == (g >> 1)), pbit = (bit)
#define PBIT0(w) (((w) & ~pm0) | (pbit & pm0))
#define PBIT1(w) (w)
#define LANE_CONSTS() \
    int lane; asm volatile("mov.u32 %0, %%laneid;" : "=r"(lane)); \
    const int g = lane >> 2, t = lane & 3; \
    const uint32_t srowoff = (r0 + (lane & 15)) * 128, lsw = (lane & 7) << 4, lhi = (lane >> 4) << 4, lsw2 = (lane & 6) << 3; \
    (void)g; (void)t; (void)srowoff; (void)lsw; (void)lhi; (void)lsw2;
    uint32_t stgp = 0, peer;
    asm volatile("mapa.shared::cluster.u32 %0, %1, %2;" : "=r"(peer) : "r"(sbase), "r"(rank ^ 1));
    peer -= sbase;
    const uint32_t dA0 = (((sbase & 0x3FFFF) + wg * 8192) >> 4) | 0x10000u, dB0 = ((sbase & 0x3FFFF) >> 4) | 0x2000000u;
    cluster_wait();
#define DESC(lo, hi) ((uint64_t)(uint32_t)(lo) | ((uint64_t)(hi) << 32))
#define STG_ARRIVE() { __syncwarp(); if (elect_one()) mbar_arrive_local(bar_stg); }
#define STG_WAIT() { mbar_wait(bar_stg, stgp); stgp ^= 1; }
#define PROFS() do {} while (0)
#define REL(addr) { if (elect_one()) { mbar_arrive_local(addr); asm volatile("mbarrier.arrive.shared::cluster.b64 _, [%0];" :: "r"((addr) + peer) : "memory"); } }
#define QSTEP(ACC, DA, SC, PRE) { \
      const uint32_t da = (DA), db = dB0 + (ub & 0x18) * (QST >> 7); \
      mbar_wait(ub, par); \
      PRE; \
      wgmma_fence(); \
      wgmma4_n192<SC>(ACC, da, db); \
      wgmma_commit(); PROFS(); }
#define QREL() { wgmma_wait<1>(); REL(ub + 376); ub += 8; }
#define RA_CUR (dA0 + (OFF_RA >> 4) + (ub & 0x18) * (SLOT >> 7))
#define PUMP1() { QSTEP(S1, RA_CUR, 1, {}); QREL(); }
#define PUMP0() { PUMP1(); SCHED_FENCE(); }
#define PUMP() if (h == 0) PUMP1()
#define WSTEP() { \
      const uint32_t s4 = (ub - bar_full - 256) >> 1; \
      const uint32_t da = dA0 + (((uint32_t)(WO_ASLOT(par) >> s4) & 15) << 10), db = dB0 + (((uint32_t)(WO_BSLOT >> s4) & 15) << 10); \
      mbar_wait(ub, par); \
      wgmma_fence(); \
      wgmma4_n128<1>(S1, da, db); \
      wgmma_commit(); PROFS(); \
      wgmma_wait<1>(); \
      if (s4) REL(ub + 376); \
      ub += 8; }
#define PUMPS(n) { _Pragma("unroll 1") for (int i_ = 0; i_ < (n); i_++) PUMP1(); }
#define SITE(n) { if ((BMASK >> (n)) & 1) PUMP1(); SCHED_FENCE(); }
#define LNSTEP(ACC, hh) { wgmma_fence(); wgmma_n192<1, 0>(ACC, make_desc(sbase + OFF_LNA + wg * 1024, 0, 128) ^ (1ull << 62), make_desc(sbase + OFF_LNB + (hh) * 4096, 0, 128) ^ (1ull << 62)); }
#define WARP_STORE(tm, tile, col, row) { fence_proxy_async_smem(); __syncwarp(); \
      if (elect_one()) { tma_store_2d(tm, (tile) + r0 * 128, col, (row) + r0); asm volatile("cp.async.bulk.commit_group;" ::: "memory"); } __syncwarp(); }
#define PUBLISH_O() WARP_STORE(&tm_os, pO, jj * 128 + h * 64, mm * 128)
#define TILE_CONSTS(base, on, bit) \
      uint32_t ta[5]; \
      { PMASKS(on, bit); (void)pbit; ta[4] = pm0; } \
      _Pragma("unroll") for (int j = 0; j < 4; j++) ta[j] = (base) + srowoff + ((((uint32_t)j << 5) + lhi) ^ lsw); \
      PINU(ta, 5); SCHED_FENCE(); \
      const uint32_t pm0 = ta[4], pbit = (bit)
#define X_OUT(pc, W) { \
      _Pragma("unroll") for (int j = 0; j < 4; j++) \
        stsm_x4(ta[j] + (pc) * SLOT, \
                PBIT0(pack_bf16((W)[j * 8 + 0], (W)[j * 8 + 1])), PBIT0(pack_bf16((W)[j * 8 + 2], (W)[j * 8 + 3])), \
                PBIT1(pack_bf16((W)[j * 8 + 4], (W)[j * 8 + 5])), PBIT1(pack_bf16((W)[j * 8 + 6], (W)[j * 8 + 7]))); }
#define REST_P1(SKEW) { \
      mbar_wait(bar_stat2, par); \
      LNSTEP(S1, 1); \
      _Pragma("unroll 1") while (ub < bar_full + 256) { \
        if (ub == bar_full + 256 - 8 * (SKEW) && wg == 0) bar_sync<BAR_SKEW, 256>(); \
        QSTEP(S1, RA_CUR, 1, {}); \
        if (ub == bar_full + 248 && wg == 1) bar_arrive<BAR_SKEW, 256>(); \
        QREL(); \
      } \
      mbar_wait(bar_done + (31 - (SKEW)) * 8, par);        \
      wgmma_wait<0>(); \
      ACC_FENCE(S1, 96); \
      REL(bar_done + 31 * 8); \
      PROF(13); }
#define FOLD(tile, rd) { \
          LANE_CONSTS(); \
          float d[32]; \
          ACC_DEF(d, 32); \
          mbar_wait(bar_phi, 0); \
          wgmma_fence(); \
          _Pragma("unroll") for (int i = 0; i < 2; i++) { \
            const uint64_t da = make_desc((tile) + wg * 8192 + i * 64, 16, 1024); \
            const uint64_t db = make_desc(sbase + OFF_PHI + wg * 4096 + i * 2048, 16, 512) ^ (3ull << 62); \
            wgmma_n32<0>(d + i * 16, da, db); wgmma_n32<1>(d + i * 16, da + 2, db + 64); \
          } \
          wgmma_commit(); \
          PUMP0(); \
          ACC_FENCE(d, 32); \
          bar_wg(wg); \
          _Pragma("unroll") for (int i = 0; i < 4; i++) { \
            const float* x = d + (i & 1) * 8 + (i >> 1) * 2; \
            if (rd) sts128((tile) + wg * 8192 + ((warp & 3) * 16 + (i >> 1) * 8 + g) * 128 + (((2 * t + (i & 1)) ^ g) << 4), \
                           pack_bf16(x[0], x[1]), pack_bf16(x[4], x[5]), pack_bf16(x[16], x[17]), pack_bf16(x[20], x[21])); \
            else stsm_x4((tile) + srowoff + ((((uint32_t)i << 5) + lhi) ^ lsw), pack_bf16(d[i * 8], d[i * 8 + 1]), pack_bf16(d[i * 8 + 2], d[i * 8 + 3]), \
                         pack_bf16(d[i * 8 + 4], d[i * 8 + 5]), pack_bf16(d[i * 8 + 6], d[i * 8 + 7])); \
          } \
          }
#define LOAD_X0(base) \
      _Pragma("unroll") for (int j = 0; j < 8; j++) { \
        uint32_t x0, x1, x2, x3; \
        ldsm_x4((base) + (j >> 2) * SLOT + srowoff + ((((uint32_t)(j & 3) << 5) + lhi) ^ lsw), x0, x1, x2, x3); \
        S1[j * 8 + 0] = bf_lo(x0); S1[j * 8 + 1] = bf_hi(x0); S1[j * 8 + 2] = bf_lo(x1); S1[j * 8 + 3] = bf_hi(x1); \
        S1[j * 8 + 4] = bf_lo(x2); S1[j * 8 + 5] = bf_hi(x2); S1[j * 8 + 6] = bf_lo(x3); S1[j * 8 + 7] = bf_hi(x3); \
      }
#define XM_ISSUE(keep) { mbar_wait(bar_xr, par); wgmma_fence(); \
      wgmma_copy(T_, dA0 + (OFF_RA >> 4), ((keep) ? make_desc(sbase + OFF_ID + 128, 0, 0) : make_desc(sbase + OFF_ID, 128, 128)) ^ (1ull << 62), keep); }
#define COPYN(d, s, n) _Pragma("unroll") for (int i_ = 0; i_ < (n); i_++) { uint32_t c_; asm volatile("mov.b32 %0, %1;" : "=r"(c_) : "f"((s)[i_])); (d)[i_] = __uint_as_float(c_); }
#define COPY64(d, s) COPYN(d, s, 64)
#define XM_DONE(c) { ACC_FENCE(T_, 64); COPY64(S1, T_); ACC_FENCE(S1, 64); \
      __syncwarp(); if ((c) && elect_one()) mbar_arrive_local(bar_lx); }
#define LOAD_X() { float T_[64]; ACC_DEF(T_, 64); wgmma_wait<0>(); XM_ISSUE(0); wgmma_commit(); wgmma_wait<0>(); XM_DONE(true); }

    float S0[96], S1[96];
#define FIRST_STEP(l_) { const int ln_ = (l_), l = ln_; const uint32_t par = l & 1, ub = bar_full; ACC_DEF(S0, 96); QSTEP(S0, dA0 + (OFF_S >> 4), 0, {}); }
    FIRST_STEP(0);
    LOAD_EPOCH();
#pragma unroll 1
    for (int l = 0;; l++) {
      const uint32_t par = l & 1;
      uint32_t ub = bar_full + 8;
      PROF(1);
      {
        LANE_CONSTS();
        uint32_t ta[4];
#pragma unroll
        for (int j = 0; j < 4; j++) ta[j] = pK + srowoff + ((((uint32_t)j << 5) + lhi) ^ lsw);
        float p0, p1, a0 = 0.f, a1 = 0.f, q0 = 0.f, q1 = 0.f;
#define STATS(j0, j1) _Pragma("unroll") for (int j = (j0); j < (j1); j++) { \
          uint32_t x[4]; \
          ldsm_x4(ta[j & 3] + (j >> 2) * SLOT, x[0], x[1], x[2], x[3]); \
          if (j == 0) { p0 = __shfl_sync(0xffffffffu, bf_lo(x[0]), lane & 28); p1 = __shfl_sync(0xffffffffu, bf_lo(x[1]), lane & 28); } \
          _Pragma("unroll") for (int i = 0; i < 4; i += 2) { \
            const float d0 = bf_lo(x[i]) - p0, d1 = bf_hi(x[i]) - p0, d2 = bf_lo(x[i + 1]) - p1, d3 = bf_hi(x[i + 1]) - p1; \
            a0 += d0 + d1; a1 += d2 + d3; \
            q0 = fmaf(d1, d1, fmaf(d0, d0, q0)); q1 = fmaf(d3, d3, fmaf(d2, d2, q1)); } } \
          asm volatile("" : "+f"(a0), "+f"(a1), "+f"(q0), "+f"(q1), "+f"(p0), "+f"(p1)); SCHED_FENCE()
        if (SB0) { STATS(0, SB0); }
        bar_wg(wg);
        QSTEP(S0, dA0 + ((OFF_S + SLOT) >> 4), 1, {});
        QREL();
        SCHED_FENCE();
        STATS(SB0, SB1);
        ACC_DEF(S1, 96);
        QSTEP(S1, dA0 + (OFF_S >> 4), 0, {});
        QREL();
        SCHED_FENCE();
        STATS(SB1, SB2);
        QSTEP(S1, dA0 + ((OFF_S + SLOT) >> 4), 1, {});
        QREL();
        SCHED_FENCE();
        STATS(SB2, 8);
#pragma unroll
        for (int o = 1; o <= 2; o <<= 1) {
          a0 += __shfl_xor_sync(0xffffffffu, a0, o); a1 += __shfl_xor_sync(0xffffffffu, a1, o);
          q0 += __shfl_xor_sync(0xffffffffu, q0, o); q1 += __shfl_xor_sync(0xffffffffu, q1, o);
        }
        if (t == 1) { a0 = a1; q0 = q1; p0 = p1; }
        if (t < 2) st_b64(g_stats + (size_t)(mm * 128 + r0 + g + t * 8) * 8 + jj, __float_as_uint(fmaf(a0, 1.f / 128.f, p0)),
                          (__float_as_uint(fmaxf(fmaf(a0 * (-1.f / 128.f), a0, q0), 0.f)) & ~3u) | STAT_TAG(l));
        if (l) { asm volatile("cp.async.bulk.wait_group 0;" ::: "memory"); bar_arrive<BAR_X1, 288>(); }
#pragma unroll 1
        for (int i = 0; i < 14; i++) {
          QSTEP(S0, RA_CUR, 1, {});
          if (i == 0) PROF(2);
          QREL();
        }
      }
      LANE_CONSTS();
      mbar_wait(bar_stat, par);
      LNSTEP(S0, 0);
      wgmma_commit();
      const float rs0 = lds32f(sbase + OFF_ST + (r0 + g) * 4), rs1 = lds32f(sbase + OFF_ST + (r0 + g + 8) * 4);
      PUMP0();
      ACC_FENCE(S0, 96);
      PROF(3);
      if (!par) {
        constexpr uint32_t par = 0;
        uint32_t qa[16];
        uint32_t kf[32], vf[32];
#define DRAIN_A(ACC, hp, PMP) { \
          LANE_CONSTS(); \
          FRAG(kf + 16, ACC + 32, 0, (hp) * 2); \
          PMP; \
          FRAG(vf + 16, ACC + 64, 1, (hp) * 2 + 1); \
          _Pragma("unroll") for (int i_ = 0; i_ < 16; i_++) qa[i_] = pack_bf16(ACC[2 * i_], ACC[2 * i_ + 1]); \
          PINU(qa, 16); }
        DRAIN_A(S0, 0, PUMP0());
        if (l == 0 && NLAYERS > 1) {
#pragma unroll 1
          for (int rd = 1; rd >= 0; rd--) {
            FOLD(sbase + (12 - rd) * SLOT, rd);
            fence_proxy_async_smem();
            asm volatile("bar.arrive %0, 288;" :: "r"(BAR_WF + 1 - rd) : "memory");
          }
        }
        PUMPS(FPUMP);
        if (l == 0 && NLAYERS > 1) mbar_wait(bar_phi, 1);
#pragma unroll 1
        for (int h = 0; h < 2; h++) {
          const uint32_t pO = sbase + (h ? 3 : 12) * SLOT;
          PROFH(4, 16);
          LANE_CONSTS();
          if (XA && h) {
            float T_[64];
            ACC_DEF(T_, 64);
            if (XA == 2) { FRAG_PUT(kf + 16, 10); }
            XM_ISSUE(0); wgmma_commit();
            SCHED_FENCE();
            if (XA == 1) { FRAG_PUT(kf + 16, 10); }
            FRAG_PUT(vf + 16, 11);
            STG_ARRIVE();
            SCHED_FENCE();
            wgmma_wait<0>(); XM_DONE(true);
          } else {
            FRAG_PUT(kf + 16, 10); FRAG_PUT(vf + 16, 11);
            STG_ARRIVE();
          }
          if (h) { if (!XA && AW0 < 4) LOAD_X(); if (AW0 == 1) WSTEP(); } else PUMPS(HPUMP2);
          const bool e = g & 1, hb = (2 * t + (g & 1)) <= g;
          uint32_t sel[3] = {e ? 0x1044u : 0x4410u, hb ? 0x4444u : (e ? 0x3244u : 0x4432u), hb ? (e ? 0x3244u : 0x4432u) : 0x4444u};
          PINU(sel, 3);
          TILE_CONSTS(pO, true, O_BIT(l));
          const uint32_t selA = sel[0], selL = sel[1], selH = sel[2];
          STG_WAIT();
          if (warp == 0) mbar_wait(bar_halo, h);
          FRAG_GET(kf, 10);
          PROFH(5, 17);
          float s[2][4][4];
#pragma unroll
          for (int ks = 0; ks < 2; ks++)
#pragma unroll
            for (int i = 0; i < 8; i++) {
              const int hh = (i >> 1) & 1, jb = (i & 1) + (~i >> 1 & 2);
              const uint32_t* b = kf + (jb >> 1) * 16 + hh * 8 + ks * 4 + (jb & 1) * 2;
              if (ks) mma_bf16(s[hh][jb], qa[hh * 8 + 4], qa[hh * 8 + 5], qa[hh * 8 + 6], qa[hh * 8 + 7], b[0], b[1]);
              else mma_bf16_z(s[hh][jb], qa[hh * 8], qa[hh * 8 + 1], qa[hh * 8 + 2], qa[hh * 8 + 3], b[0], b[1]);
            }
          if (h == 0) PUMP1() else if (AW0 == 2 || AW0 == 4) { if (AW0 == 4) LOAD_X(); WSTEP(); }
          PROFH(6, 18);
          float va[2][2], vb[2][2], mx[2][2];
#pragma unroll
          for (int hh = 0; hh < 2; hh++) {
            va[hh][0] = e ? s[hh][1][1] : s[hh][1][0];
            vb[hh][0] = hb ? (e ? s[hh][2][1] : s[hh][2][0]) : (e ? s[hh][0][1] : s[hh][0][0]);
            va[hh][1] = e ? s[hh][2][3] : s[hh][2][2];
            vb[hh][1] = hb ? (e ? s[hh][3][3] : s[hh][3][2]) : (e ? s[hh][1][3] : s[hh][1][2]);
          }
          if (warp == 0 && mm == 0) {
#pragma unroll
            for (int hh = 0; hh < 2; hh++) { va[hh][0] = -INFINITY; if (!hb) { vb[hh][0] = -INFINITY; vb[hh][1] = -INFINITY; } }
          }
#pragma unroll
          for (int i = 0; i < 4; i++) mx[i >> 1][i & 1] = fmaxf(va[i >> 1][i & 1], vb[i >> 1][i & 1]);
#pragma unroll
          for (int o = 1; o <= 2; o <<= 1)
#pragma unroll
            for (int i = 0; i < 4; i++) mx[i >> 1][i & 1] = fmaxf(mx[i >> 1][i & 1], __shfl_xor_sync(0xffffffffu, mx[i >> 1][i & 1], o));
          const float sc0 = rs0 * (0.17677669529663687f * LOG2E), sc1 = rs1 * (0.17677669529663687f * LOG2E);
#pragma unroll
          for (int i = 0; i < 4; i++) {
            const float sc = (i & 1) ? sc1 : sc0, m = mx[i >> 1][i & 1];
            va[i >> 1][i & 1] = ex2((va[i >> 1][i & 1] - m) * sc); vb[i >> 1][i & 1] = ex2((vb[i >> 1][i & 1] - m) * sc);
            mx[i >> 1][i & 1] = va[i >> 1][i & 1] + vb[i >> 1][i & 1];
          }
          if (h == 0 && ASITE) { PIN(&va[0][0], 4); PIN(&vb[0][0], 4); PIN(&mx[0][0], 4); PUMP1(); } else if (AW0 == 3) WSTEP();
          if (warp == 0) mbar_wait(bar_halo + 8, h);
          FRAG_GET(vf, 11);
#pragma unroll
          for (int o = 1; o <= 2; o <<= 1)
#pragma unroll
            for (int i = 0; i < 4; i++) mx[i >> 1][i & 1] += __shfl_xor_sync(0xffffffffu, mx[i >> 1][i & 1], o);
          float o[2][4][4];
          uint32_t pa[2][8];
#pragma unroll
          for (int hh = 0; hh < 2; hh++) {
            const float i0 = rcp_fast(mx[hh][0]), i1 = rcp_fast(mx[hh][1]);
            const uint32_t w0 = pack_bf16(va[hh][0] * i0, vb[hh][0] * i0), w1 = pack_bf16(va[hh][1] * i1, vb[hh][1] * i1);
            pa[hh][0] = __byte_perm(w0, 0, selL); pa[hh][2] = __byte_perm(w0, 0, selA); pa[hh][3] = __byte_perm(w1, 0, selL);
            pa[hh][4] = __byte_perm(w0, 0, selH); pa[hh][5] = __byte_perm(w1, 0, selA); pa[hh][7] = __byte_perm(w1, 0, selH);
            pa[hh][1] = pa[hh][0] & pa[hh][4]; pa[hh][6] = pa[hh][3] & pa[hh][7];
          }
          PROFH(7, 19);
#pragma unroll
          for (int i = 0; i < 8; i++) mma_bf16_z(o[i >> 2][i & 3], pa[i >> 2][4], pa[i >> 2][5], pa[i >> 2][6], pa[i >> 2][7], vf[16 + 2 * i], vf[17 + 2 * i]);
#pragma unroll
          for (int i = 0; i < 8; i++) mma_bf16(o[i >> 2][i & 3], pa[i >> 2][0], pa[i >> 2][1], pa[i >> 2][2], pa[i >> 2][3], vf[2 * i], vf[2 * i + 1]);
          if (h == 0) PUMP1() else mbar_wait(bar_done + 30 * 8, par);
          if (NLAYERS > 1) mbar_wait(bar_phi + 8, 0);
#pragma unroll
          for (int i = 0; i < 4; i++) {
            const int hh = i >> 1, dp = i & 1;
            stsm_x4(ta[i],
                    PBIT0(pack_bf16(o[hh][dp * 2][0], o[hh][dp * 2][1])), PBIT0(pack_bf16(o[hh][dp * 2][2], o[hh][dp * 2][3])),
                    PBIT1(pack_bf16(o[hh][dp * 2 + 1][0], o[hh][dp * 2 + 1][1])), PBIT1(pack_bf16(o[hh][dp * 2 + 1][2], o[hh][dp * 2 + 1][3])));
          }
          PUBLISH_O();
          PROFH(11, 23);
          if (h) break;
          REST_P1(ASKEW);
          asm volatile("cp.async.bulk.wait_group.read 0;" ::: "memory");
          DRAIN_A(S1, 1, {});
        }
      } else {
        constexpr uint32_t par = 1;
        float st[32];
        const float c0 = rs0 * LOG2E, c1 = rs1 * LOG2E;
        { V_ADDR(pV); STAGE_V(S0 + 64); }
        if (warp < 2) sts128(sbase + OFF_ONES + warp * 512 + lane * 16, 0x3F803F80u, 0x3F803F80u, 0x3F803F80u, 0x3F803F80u);
        scale32(st, S0, c0, c1);
        PIN(st, 32);
#define PHI_PIECE(c) { \
          e_[2 * (c)] = ex2(st[2 * (c)]); e_[2 * (c) + 1] = ex2(st[2 * (c) + 1]); \
          _Pragma("unroll") for (int k_ = 4 * (c); k_ < 4 * (c) + 4; k_++) m_[(c) >> 1] = (k_ & 7) ? fmaf(st[k_], st[k_], m_[(c) >> 1]) : st[k_] * st[k_]; \
          asm volatile("" : "+f"(e_[2 * (c)]), "+f"(e_[2 * (c) + 1]), "+f"(m_[(c) >> 1])); SCHED_FENCE(); }
#define PHI_FIN() { \
          big = __any_sync(0xffffffffu, !(fmaxf(fmaxf(m_[0], m_[1]), fmaxf(m_[2], m_[3])) < BIGLIM)); \
          if (__builtin_expect(big, 0)) { COPYN(e_, st, 16); } \
          _Pragma("unroll") for (int k_ = 0; k_ < 16; k_++) st[k_] = e_[k_]; \
          PIN(st, 16); }
#define KV_MMA(vs, IL) { \
          const uint32_t dp = dA0 + 12 * 1024 - wg * 2560, dv = dA0 + (vs) * 1024 + ((OFF_ONES - (vs) * SLOT - 16) << 12) - wg * (512 << 16); \
          STG_WAIT(); \
          wgmma_fence(); \
          _Pragma("unroll") for (int ks = 0; ks < 8; ks++) { \
            const uint64_t a = DESC(dp + ks * 128, 0x40000040), b = DESC(dv + ks * (64 - (64 << 16)), 0x80000020); \
            if ((IL) && ks) wgmma_fence(); \
            if (ks == 0) wgmma_n40<0, 1>(kv, a, b); else wgmma_n40<1, 1>(kv, a, b); \
            if (ks == 7) wgmma_commit(); \
            if (IL) PHI_PIECE(ks); } }
#define KV_RED(hp) { \
          float* kvg = g_kv[l >> 1] + (jj * 4 + (hp) * 2) * KVH + warp * 768 + lane * 4; \
          _Pragma("unroll") for (int i = 0; i < 5; i++) red_v4(kvg + i * 128, kv[i * 3], kv[i * 3 + 1], kv[i * 3 + 2], 1.f); \
          red_v4(kvg + 640, kv[15], kv[16], kv[18], 1.f); }
#define KV_RED1(i) if (h) red_v4(g_kv[l >> 1] + (jj * 4) * KVH + warp * 768 + lane * 4 + (i) * 128, S0[32 + (i) * 3], S0[33 + (i) * 3], S0[34 + (i) * 3], 1.f)
#define KV_REDS(n) { if (PAIR & 1) { if (h && (n) == PPOS0) KV_RECV(S0 + 32, 0); } else _Pragma("unroll") for (int i_ = 0; i_ < 6; i_++) if (((RPACE >> (4 * i_)) & 15) == (n)) KV_RED1(i_); }
#define KV_SEND(kp) { \
          float sd[9]; \
          kv[17] = kv[18]; \
          _Pragma("unroll") for (int i = 0; i < 9; i++) { (kp)[i] = rank ? kv[9 + i] : kv[i]; sd[i] = rank ? kv[i] : kv[9 + i]; } \
          const uint32_t ra = sbase + peer + (warp * 32 + lane) * 4, rb = bar_kx + peer; \
          if (elect_one()) mbar_expect_tx(bar_kx, 1152); \
          _Pragma("unroll") for (int i = 0; i < 2; i++) \
            asm volatile("st.async.weak.shared::cluster.mbarrier::complete_tx::bytes.v4.f32 [%0], {%1, %2, %3, %4}, [%5];" \
                         :: "r"(ra + (warp * 32 + lane) * 12 + OFF_PHI + i * 4096), "f"(sd[4 * i]), "f"(sd[4 * i + 1]), "f"(sd[4 * i + 2]), "f"(sd[4 * i + 3]), "r"(rb) : "memory"); \
          asm volatile("st.async.weak.shared::cluster.mbarrier::complete_tx::bytes.f32 [%0], %1, [%2];" :: "r"(ra + OFF_LNB), "f"(sd[8]), "r"(rb) : "memory"); }
#define KV_RECV(kp, hp) { \
          float r_[9]; \
          float* kvg = g_kv[l >> 1] + (jj * 4 + (hp) * 2) * KVH + warp * 768 + rank * 384 + lane * 4; \
          mbar_wait(bar_kx, PAIR == 3 ? (hp) : (l >> 1)); \
          _Pragma("unroll") for (int i = 0; i < 2; i++) \
            asm volatile("ld.shared.v4.f32 {%0, %1, %2, %3}, [%4];" : "=f"(r_[4 * i]), "=f"(r_[4 * i + 1]), "=f"(r_[4 * i + 2]), "=f"(r_[4 * i + 3]) \
                         : "r"(sbase + OFF_PHI + i * 4096 + (warp * 32 + lane) * 16) : "memory"); \
          r_[8] = lds32f(sbase + OFF_LNB + (warp * 32 + lane) * 4); \
          _Pragma("unroll") for (int i = 0; i < 3; i++) red_v4(kvg + i * 128, (kp)[3 * i] + r_[3 * i], (kp)[3 * i + 1] + r_[3 * i + 1], (kp)[3 * i + 2] + r_[3 * i + 2], 2.f); }
#define KV_LOAD(hp) { \
          const uint4* kvg = reinterpret_cast<const uint4*>(g_kv[l >> 1] + (jj * 4 + (hp) * 2) * KVH) + warp * 192 + lane; \
          _Pragma("unroll") for (int i = 0; i < 6; i++) v[i] = ld_b128(kvg + i * 32); }
#define KVV(i) __uint_as_float((i) % 3 == 0 ? v[(i) / 3].x : ((i) % 3 == 1 ? v[(i) / 3].y : v[(i) / 3].z))
#define KV_TILE(hp) { \
          _Pragma("unroll 1") for (int it = 0; it < (1 << 16); it++) { \
            if (__all_sync(0xffffffffu, (v[0].w & v[1].w & v[2].w & v[3].w & v[4].w & v[5].w) == 0x41800000u)) break; \
            RETRY_COUNT(); \
            KV_LOAD(hp); \
          } \
          if (hp) PROF(26); else PROF(25); \
          const uint32_t e = lane & 7, jt = ((lane >> 1) & 4) + (e >> 1); \
          const uint32_t row = ((((warp >> 1) ^ wg) & 1) << 5) + ((jt & 1) << 4) + ((warp & 1) << 3) + (jt & 6) + (e & 1); \
          const uint32_t kd = pV + wg * 8192 + row * 128, ksw = (row & 7) << 4; \
          _Pragma("unroll") for (int i = 0; i < 2; i++) \
            stsm_x4(kd + ((i * 32 + lhi) ^ ksw), pack_bf16(KVV(i * 8), KVV(i * 8 + 1)), pack_bf16(KVV(i * 8 + 2), KVV(i * 8 + 3)), \
                    pack_bf16(KVV(i * 8 + 4), KVV(i * 8 + 5)), pack_bf16(KVV(i * 8 + 6), KVV(i * 8 + 7))); \
          stsm_x4(kd + ((64u + lhi) ^ ksw), pack_bf16(KVV(16), 1.f), pack_bf16(KVV(17), 1.f), 0u, 0u); }
#pragma unroll 1
        for (int h = 0; h < 2; h++) {
          PROFH(4, 6);
          SITE(0);
          LANE_CONSTS();
          const uint32_t dsw = (uint32_t)(g ^ (2 * t)) << 4, dst = ((t & 2) ? pK : sbase + 12 * SLOT) + (r0 + g) * 128;
          float e[16], f[16];
          KV_REDS(1);
          float sa = exps16_<0>(e, st);
          exps16_fix<0>(e, st, sa);
          asm volatile("" : "+f"(sa)); PIN(e, 16); SITE(1);
          if (h) STG_WAIT();
          KV_REDS(2);
          store16(e, sa, dst, dsw, 4);
          float sb = exps16_<1>(f, st);
          exps16_fix<1>(f, st, sb);
          asm volatile("" : "+f"(sb)); PIN(f, 16); SITE(2);
          KV_REDS(3);
          store16(f, sb, dst, dsw, 0);
          float sc = exps16_<0>(e, st + 2);
          exps16_fix<0>(e, st + 2, sc);
          asm volatile("" : "+f"(sc)); PIN(e, 16); SITE(3);
          KV_REDS(4);
          store16(e, sc, dst + 1024, dsw, 4);
          float sd = exps16_<1>(f, st + 2);
          exps16_fix<1>(f, st + 2, sd);
          asm volatile("" : "+f"(sd)); PIN(f, 16); SITE(4);
          store16(f, sd, dst + 1024, dsw, 0);
          PROFH(5, 7);
          if (h) break;
          {
            float kv[20];
            ACC_DEF(kv, 20);
            fence_proxy_async_smem();
            STG_ARRIVE();
            float e_[16], m_[4];
            KV_MMA(11, 0);
            PUMP0();
            ACC_FENCE(kv, 20);
            STG_ARRIVE();
            scale32(st, S0 + 32, c0, c1);
            PIN(st, 32);
            if (PAIR & 1) { KV_SEND(S0 + 32); PIN(S0 + 32, 9); }
            else {
              kv[17] = kv[18];
              COPYN(S0 + 32, kv, 18);
              const int h = 1;
              KV_REDS(0);
            }
          }
        }
        bool big;
        uint4 v[6];
        {
          float kv[20];
          if (KT0) { LANE_CONSTS(); KV_LOAD(0); }
          mbar_wait(bar_stat2, par);
          LNSTEP(S1, 1);
          ub = bar_full + 240;
          PUMP1();
          if (wg == 0) bar_sync<BAR_SKEW, 256>();
          QSTEP(S1, RA_CUR, 1, {});
          if (wg == 1) bar_arrive<BAR_SKEW, 256>();
          QREL();
          if (KT0 == 2) { LANE_CONSTS(); KV_TILE(0); }
          LANE_CONSTS();
          V_ADDR(sbase + 3 * SLOT);
          PINU(va_, 2);
          mbar_wait(bar_done + 30 * 8, par);
          wgmma_wait<0>();
          ACC_FENCE(S1, 96);
          if (!(RLATE & 2)) REL(bar_done + 31 * 8);
          PROF(13);
          STAGE_V(S1 + 64);
          fence_proxy_async_smem();
          STG_ARRIVE();
          if (RLATE & 2) REL(bar_done + 31 * 8);
          scale32(st, S1, c0, c1);
          PIN(st, 32);
          PROF(16);
          ACC_DEF(kv, 20);
          float e_[16], m_[4];
          KV_MMA(3, ILV & 1);
          SCHED_FENCE();
          PROF(14);
          if (ILV & 1) PHI_FIN() else if (!SEARLY) { big = any_big(st); phiq_a(st, big); PIN(st, 16); }
          if (SEARLY == 2) big = any_big(st);
          SCHED_FENCE();
          PROF(15);
          wgmma_wait<0>();
          ACC_FENCE(kv, 20);
          PROF(12);
          if (PAIR & 2) { float kp[9]; KV_SEND(kp); _Pragma("unroll") for (int i = 0; i < 3; i++) v[i] = make_uint4(__float_as_uint(kp[3 * i]), __float_as_uint(kp[3 * i + 1]), __float_as_uint(kp[3 * i + 2]), 0u); }
          else KV_RED(1);
          if (SEARLY) { SCHED_FENCE(); if (SEARLY == 1) big = any_big(st); phiq_a(st, big); PIN(st, 16); SCHED_FENCE(); }
          PROF(17);
        }
#pragma unroll 1
        for (int h = 0; h < 2; h++) {
          const uint32_t pO = sbase + (h ? 3 : 8) * SLOT;
          LANE_CONSTS();
          uint32_t fq[32];
#define KV_RECV1(pos) if ((PAIR & 2) && PPOS == (pos) && h == 0) { float kp[9]; _Pragma("unroll") for (int i = 0; i < 9; i++) kp[i] = KVV(i); KV_RECV(kp, 1); SCHED_FENCE(); }
          PROFH(18, 32);
          SCHED_FENCE();
          if (NEWO) { phiq_b<1>(fq, st, big); PINU(fq, 16); PIN(st + 16, 16); SCHED_FENCE(); PROFH(8, 9); }
          if (h) {
            asm volatile("cp.async.bulk.wait_group.read 0;" ::: "memory");
            mbar_wait(bar_lx, par);
            PROF(30);
            KV_TILE(1);
            fence_proxy_async_smem();
            STG_ARRIVE();
          }
          SCHED_FENCE();
          if (!NEWO) { phiq_b<1>(fq, st, big); PINU(fq, 16); PIN(st + 16, 16); PROFH(8, 9); }
          KV_RECV1(1);
          if (NEWO & 1) { phiq_b<0>(fq + 16, st + 16, big); PINU(fq + 16, 16); PROFH(10, 21); }
          if (h) STG_WAIT();
          wgmma_wait<0>();
          ACC_FENCE(S1, 64);
          PROFH(19, 33);
          float o[4][20];
#define O_MMA(hh) { \
            const uint64_t db = make_desc(pV + (hh) * 8192, 16, 1024); \
            ACC_DEF(o[(hh) * 2], 20); ACC_DEF(o[(hh) * 2 + 1], 20); \
            wgmma_fence(); \
            wgmma_n40_rs<0>(o[(hh) * 2], fq + (hh) * 16, db + 256); wgmma_n40_rs<0>(o[(hh) * 2 + 1], fq + (hh) * 16 + 8, db); \
            wgmma_n40_rs<1>(o[(hh) * 2], fq + (hh) * 16 + 4, db + 384); wgmma_n40_rs<1>(o[(hh) * 2 + 1], fq + (hh) * 16 + 12, db + 128); \
            wgmma_commit(); }
          O_MMA(0);
          if (NEWO == 1) O_MMA(1);
          SCHED_FENCE();
          if (!(NEWO & 1)) { phiq_b<0>(fq + 16, st + 16, big); PINU(fq + 16, 16); PROFH(10, 21); }
          SCHED_FENCE();
          PMASKS(true, O_BIT(l));
#pragma unroll
          for (int hh = 0; hh < 2; hh++) {
            if (NEWO == 1 && !hh) wgmma_wait<1>(); else wgmma_wait<0>();
            ACC_FENCE(o[hh * 2], 20); ACC_FENCE(o[hh * 2 + 1], 20);
            if (!hh && NEWO != 1) { O_MMA(1); SCHED_FENCE(); }
            if (hh) PROFH(22, 24);
            const float* x = o[hh * 2];
            const float* y = o[hh * 2 + 1];
            const float sx0 = x[17] * 0x1p-40f, sy0 = y[17] * 0x1p-40f, sx1 = x[19] * 0x1p-40f, sy1 = y[19] * 0x1p-40f;
            const float i0 = rcp_fast(fmaf(fmaf(x[17], 1e-6f, x[16]), sy0, y[16] * sx0)), i1 = rcp_fast(fmaf(fmaf(x[19], 1e-6f, x[18]), sy1, y[18] * sx1));
            const float ax0 = sy0 * i0, ay0 = sx0 * i0, ax1 = sy1 * i1, ay1 = sx1 * i1;
#pragma unroll
            for (int dp = 0; dp < 2; dp++)
              stsm_x4(pO + srowoff + ((hh * 64 + dp * 32 + lhi) ^ lsw),
                      PBIT0(pack_bf16(fmaf(x[dp * 8], ax0, y[dp * 8] * ay0), fmaf(x[dp * 8 + 1], ax0, y[dp * 8 + 1] * ay0))),
                      PBIT0(pack_bf16(fmaf(x[dp * 8 + 2], ax1, y[dp * 8 + 2] * ay1), fmaf(x[dp * 8 + 3], ax1, y[dp * 8 + 3] * ay1))),
                      PBIT1(pack_bf16(fmaf(x[dp * 8 + 4], ax0, y[dp * 8 + 4] * ay0), fmaf(x[dp * 8 + 5], ax0, y[dp * 8 + 5] * ay0))),
                      PBIT1(pack_bf16(fmaf(x[dp * 8 + 6], ax1, y[dp * 8 + 6] * ay1), fmaf(x[dp * 8 + 7], ax1, y[dp * 8 + 7] * ay1))));
          }
          PUBLISH_O();
          PROFH(20, 34);
          if (h) break;
          float T_[64];
          scale32(st, S1 + 32, c0, c1);
          PIN(st, 32);
          ACC_DEF(T_, 64);
          if (ILV & 2) {
            float e_[16], m_[4];
            if (KVL == 0) KV_LOAD(1);
            mbar_wait(bar_xr, par);
#pragma unroll
            for (int j = 0; j < 8; j++) {
              wgmma_fence();
              wgmma_n16<0>(T_ + j * 8, DESC(dA0 + (OFF_RA >> 4) + (j >> 2) * 1024 + (j & 3) * 2, 0x40000040), make_desc(sbase + OFF_ID, 128, 128) ^ (1ull << 62));
              if (j == 7) wgmma_commit();
              PHI_PIECE(j);
            }
            if (KVL == 1) KV_LOAD(1);
            PHI_FIN();
          } else {
            XM_ISSUE(0); wgmma_commit();
            SCHED_FENCE();
            if (KVL < 2) KV_LOAD(1);
            if (ILV & 4) {
              float e_[16];
#pragma unroll
              for (int j = 0; j < 16; j++) e_[j] = ex2(st[j]);
              big = any_big(st);
              if (__builtin_expect(big, 0)) { COPYN(e_, st, 16); }
#pragma unroll
              for (int j = 0; j < 16; j++) st[j] = e_[j];
              PIN(st, 16);
            } else big = any_big(st);
          }
          SCHED_FENCE();
          PROF(27);
          wgmma_wait<0>(); XM_DONE(true);
          PROF(28);
          bar_wg(wg);
          WSTEP();
          SCHED_FENCE();
          PROF(29);
          if (KVL == 2) KV_LOAD(1);
          if (!(ILV & 6)) { phiq_a(st, big); PIN(st, 16); }
          PROF(31);
        }
      }
      __syncwarp();
      if (elect_one()) mbar_arrive_local(bar_epi);
      bar_wg(wg);
#pragma unroll 1
      while (ub < bar_full + 384) {
        WSTEP();
        if (ub == bar_full + 8 * 41) { asm volatile("cp.async.bulk.wait_group.read 0;" ::: "memory"); PROF(35); }
        if (ub == bar_full + 8 * 42) PROF(36);
      }
      {
        float Wb[32];
        LANE_CONSTS();
        TILE_CONSTS(pK, l < NLAYERS - 1, X_BIT(l));
        wgmma_wait<0>();
        ACC_FENCE(S1, 64);
        COPYN(Wb, S1 + 32, 32);
        PROF(37);
        X_OUT(0, S1);
        WARP_STORE(l < NLAYERS - 1 ? &tm_os : &tm_xo, pK, jj * 128, mm * 128 + (l < NLAYERS - 1 ? S_LEN : 0));
        if (l == NLAYERS - 1) { PMASKS(false, 0); X_OUT(1, Wb); break; }
        REL(bar_done + 47 * 8);
        PROF(38);
        bar_wg(wg);
        FIRST_STEP(l + 1);
        PROF(39);
        { PMASKS(false, 0); X_OUT(1, Wb); }
        fence_proxy_async_smem();
      }
    }
    WARP_STORE(&tm_xo, pV, jj * 128 + 64, mm * 128);
    asm volatile("cp.async.bulk.wait_group.read 0;" ::: "memory");
    cluster_sync();
  }
}

typedef CUresult (*PFN_encode)(CUtensorMap*, CUtensorMapDataType, cuuint32_t, void*, const cuuint64_t*, const cuuint64_t*,
                               const cuuint32_t*, const cuuint32_t*, CUtensorMapInterleave, CUtensorMapSwizzle,
                               CUtensorMapL2promotion, CUtensorMapFloatOOBfill);

CUtensorMap make_map(PFN_encode enc, const void* ptr, uint64_t inner, uint64_t outer, uint32_t box_inner, uint32_t box_outer,
                     CUtensorMapSwizzle swz = CU_TENSOR_MAP_SWIZZLE_128B, int promo = CU_TENSOR_MAP_L2_PROMOTION_L2_256B) {
  CUtensorMap m;
  cuuint64_t dims[2] = {inner, outer};
  cuuint64_t strides[1] = {inner * 2};
  cuuint32_t box[2] = {box_inner, box_outer};
  cuuint32_t es[2] = {1, 1};
  enc(&m, CU_TENSOR_MAP_DATA_TYPE_BFLOAT16, 2, const_cast<void*>(ptr), dims, strides, box, es, CU_TENSOR_MAP_INTERLEAVE_NONE,
      swz, (CUtensorMapL2promotion)promo, CU_TENSOR_MAP_FLOAT_OOB_FILL_NONE);
  return m;
}

}

extern "C" void kernel_launch(void* const* d_in, const int* in_sizes, int n_in, void* d_out, int out_size) {
  (void)in_sizes; (void)n_in; (void)out_size;
  static PFN_encode enc = nullptr;
  if (!enc) {
    void* fn = nullptr;
    cudaDriverEntryPointQueryResult qr;
    cudaGetDriverEntryPoint("cuTensorMapEncodeTiled", &fn, cudaEnableDefault, &qr);
    enc = (PFN_encode)fn;
    cudaFuncSetAttribute(mega_kernel, cudaFuncAttributeMaxDynamicSharedMemorySize, SMEM_BYTES);
  }
  Params prm;
  prm.x0 = (const __nv_bfloat16*)d_in[0];
  prm.wA_qkv = (const __nv_bfloat16*)d_in[1];
  prm.wA_o = (const __nv_bfloat16*)d_in[2];
  prm.wB_qkv = (const __nv_bfloat16*)d_in[4];
  prm.wB_phi = (const __nv_bfloat16*)d_in[5];
  prm.wB_o = (const __nv_bfloat16*)d_in[6];
  prm.out = (__nv_bfloat16*)d_out;
  void *obuf = nullptr, *wf = nullptr;
  cudaGetSymbolAddress(&obuf, g_obuf);
  cudaGetSymbolAddress(&wf, g_wfold);
  CUtensorMap tm_x0 = make_map(enc, d_in[0], D_MODEL, S_LEN, 64, 128, CU_TENSOR_MAP_SWIZZLE_128B, XPROMO);
  CUtensorMap tm_xo = make_map(enc, d_out, D_MODEL, S_LEN, 64, 16);
  CUtensorMap tm_os = make_map(enc, obuf, D_MODEL, 2 * S_LEN, 64, 16);
  CUtensorMap tm_o = make_map(enc, obuf, D_MODEL, 2 * S_LEN, 64, 128, CU_TENSOR_MAP_SWIZZLE_128B, OPROMO);
  CUtensorMap tm_wf = make_map(enc, wf, 2048, D_MODEL, 64, 32);
  CUtensorMap tm_wqA = make_map(enc, d_in[1], 3 * D_MODEL, D_MODEL, 64, 32, CU_TENSOR_MAP_SWIZZLE_128B, WPROMO);
  CUtensorMap tm_wqB = make_map(enc, prm.wB_qkv, 3 * D_MODEL, D_MODEL, 64, 32);
  CUtensorMap tm_woA = make_map(enc, prm.wA_o, D_MODEL, D_MODEL, 64, 64);
  CUtensorMap tm_woB = make_map(enc, prm.wB_o, D_MODEL, D_MODEL, 64, 64);
  CUtensorMap tm_phi = make_map(enc, prm.wB_phi, 32, 1024, 32, 128, CU_TENSOR_MAP_SWIZZLE_64B);
  mega_kernel<<<NMAIN + NAUX, 384, SMEM_BYTES>>>(tm_x0, tm_xo, tm_os, tm_o, tm_wf, tm_wqA, tm_wqB, tm_woA, tm_woB, tm_phi, prm);
}
```

```cpp
#include <cuda_runtime.h>
#include <cuda.h>
#include <cuda_bf16.h>
#include <stdint.h>

#define NLAYERS 4

#define HPUMP2 1
#define ASKEW 2
#define FPUMP 3
#define PFGAP 100
#define POLLGAP 120
#define HW1 29
#define XPACE 0x06050401000000ull
#define XP0 4
#define HW0 18
#define XD 4
#define WFGAP 50
#define EARLY 2
#define BIGLIM 3600.f
#define SUMLO 0x1p-100f
#define SUMHI 0x1p100f
#define XPROMO 2
#define OPROMO 3
#define STAG2 300
#define WPROMO 3
#define SB0 2
#define SB1 4
#define SB2 6
#define PROWS 3
#define SPD0 0
#define SPD1 0
#define SPD2 300
#define FRB 0x3535353535ull
#define NOB 0xFFFFFF00u
#define NO1 ~0u
#define NOX ~0u
#define FD0 0
#define FD1 3
#define RPACE 0x221100
namespace {

constexpr int S_LEN = 2048, D_MODEL = 1024;
constexpr int NAUX = 4, NMAIN = 128;
constexpr int SLOT = 16384;
constexpr int QST = 24576;
constexpr int OFF_RA = 6 * SLOT, OFF_S = 10 * SLOT;
constexpr int OFF_HALO = 13 * SLOT, OFF_LNB = OFF_HALO  , OFF_ONES = OFF_HALO + 3072;
constexpr int OFF_ST = OFF_HALO + 7168  , OFF_ID = OFF_HALO + 7680, OFF_PHI = OFF_HALO + 8192;
constexpr int OFF_BAR = 14 * SLOT;
constexpr int OFF_LNA = OFF_BAR + 1024;
constexpr int SMEM_BYTES = OFF_LNA + 2048;
#define WO_ASLOT(par) ((par) ? 0x9876CAB39876CA98ull : 0x98C76BA398C7698Cull)
constexpr unsigned long long WO_BSLOT = 0x5432105421054210ull;
__device__ __forceinline__ int srcb(int j, int i) { return (i + (i >= j)) & 7; }
__device__ __forceinline__ int kslice(int j, int i) { return i < 2 ? 2 * j + i : (i < 9 ? 2 * srcb(j, i - 2) : 2 * srcb(j, i - 9) + 1); }
__device__ __forceinline__ int wslice(int j, int s) { return 2 * ((s & 7) ? srcb(j, (s & 7) - 1) : j) + (s >> 3); }
constexpr int KVH = 6 * 128 * 4;

struct __align__(128) Flag { unsigned v; unsigned pad[31]; };
struct Flags {
  Flag xready[4][16];
  Flag wfready[8];
  Flag done;
  Flag epoch;
};

__device__ Flags g_flags;
__device__ __nv_bfloat16 g_obuf[2 * S_LEN * D_MODEL];
#define O_BIT(l) ((epoch * NLAYERS + (l) + 1) & 1u)
#define X_BIT(l) ((epoch * (NLAYERS - 1) + (l) + 1) & 1u)
__device__ __nv_bfloat16 g_wfold[D_MODEL * 2048];
__device__ uint4 g_halo[16 * 8 * 512];
__device__ __align__(128) float g_kv[2][32 * KVH];
__device__ __align__(128) uint2 g_colsum[2][1536][2];
__device__ __align__(128) uint2 g_stats[S_LEN * 8];
#define H_BIT(l) (NLAYERS > 2 ? (uint32_t)((l) == 0) : (ep1 & 1))
#define STAT_TAG(l) ((ep1 * NLAYERS + (l) + 1) & 3u)

#define RETRY_COUNT()
#define PRL 0
#define PRU 0
#define PROFL 1
#define PROFW 0
#define PROFT(i) do {} while (0)
#define PROF(i) do {} while (0)
#define PROFH(i, j) do {} while (0)

__device__ __forceinline__ uint32_t smem_u32(const void* p) { return (uint32_t)__cvta_generic_to_shared(p); }
__device__ __forceinline__ bool elect_one() {
  uint32_t p;
  asm volatile("{\n.reg .pred p;\nelect.sync _|p, 0xffffffff;\nselp.u32 %0, 1, 0, p;\n}\n" : "=r"(p));
  return p != 0;
}
__device__ __forceinline__ void mbar_init(uint32_t bar, uint32_t cnt) {
  asm volatile("mbarrier.init.shared::cta.b64 [%0], %1;" :: "r"(bar), "r"(cnt));
}
__device__ __forceinline__ void mbar_expect_tx(uint32_t bar, uint32_t bytes) {
  asm volatile("mbarrier.arrive.expect_tx.shared::cta.b64 _, [%0], %1;" :: "r"(bar), "r"(bytes) : "memory");
}
#define mbar_wait(bar, parity) \
  asm volatile("{\n.reg .pred p, q;\nW_%=:\nmbarrier.try_wait.parity.shared::cta.b64 p, [%1], %2;\nadd.s32 %0, %0, -1;\n" \
               "setp.gt.and.s32 q, %0, 0, !p;\n@q bra.uni W_%=;\n}\n" : "+r"(budget) : "r"((uint32_t)(bar)), "r"((uint32_t)(parity)) : "memory")
#define mbar_wait_sl(bar, parity) \
  asm volatile("{\n.reg .pred p, q;\nW_%=:\nmbarrier.try_wait.parity.shared::cta.b64 p, [%1], %2, 20000;\nadd.s32 %0, %0, -64;\n" \
               "setp.gt.and.s32 q, %0, 0, !p;\n@q bra.uni W_%=;\n}\n" : "+r"(budget) : "r"((uint32_t)(bar)), "r"((uint32_t)(parity)) : "memory")
__device__ __forceinline__ void mbar_arrive_local(uint32_t bar) {
  asm volatile("mbarrier.arrive.shared::cta.b64 _, [%0];" :: "r"(bar) : "memory");
}
__device__ __forceinline__ void tma_load_2d(uint32_t dst, const CUtensorMap* tm, uint32_t bar, int c0, int c1) {
  asm volatile("cp.async.bulk.tensor.2d.shared::cluster.global.mbarrier::complete_tx::bytes [%0], [%1, {%3, %4}], [%2];"
               :: "r"(dst), "l"(tm), "r"(bar), "r"(c0), "r"(c1) : "memory");
}
__device__ __forceinline__ void tma_load_2d_mc(uint32_t dst, const CUtensorMap* tm, uint32_t bar, int c0, int c1) {
  asm volatile("cp.async.bulk.tensor.2d.shared::cluster.global.mbarrier::complete_tx::bytes.multicast::cluster [%0], [%1, {%3, %4}], [%2], %5;"
               :: "r"(dst), "l"(tm), "r"(bar), "r"(c0), "r"(c1), "h"((uint16_t)3) : "memory");
}
__device__ __forceinline__ void tma_store_2d(const CUtensorMap* tm, uint32_t src, int c0, int c1) {
  asm volatile("cp.async.bulk.tensor.2d.global.shared::cta.bulk_group [%0, {%2, %3}], [%1];"
               :: "l"(tm), "r"(src), "r"(c0), "r"(c1) : "memory");
}
__device__ __forceinline__ void bulk_commit_wait() {
  asm volatile("cp.async.bulk.commit_group;\ncp.async.bulk.wait_group 0;" ::: "memory");
}
__device__ __forceinline__ void prefetch_tmap(const CUtensorMap* tm) {
  asm volatile("prefetch.tensormap [%0];" :: "l"(tm) : "memory");
}
__device__ __forceinline__ void fence_proxy_async_global() { asm volatile("fence.proxy.async.global;" ::: "memory"); }
__device__ __forceinline__ void fence_proxy_async_smem() { asm volatile("fence.proxy.async.shared::cta;" ::: "memory"); }
__device__ __forceinline__ unsigned ld_relaxed(const unsigned* p) {
  unsigned v;
  asm volatile("ld.relaxed.gpu.global.u32 %0, [%1];" : "=r"(v) : "l"(p) : "memory");
  return v;
}
__device__ __forceinline__ void fence_acquire() { asm volatile("fence.acquire.gpu;" ::: "memory"); }
__device__ __forceinline__ void wait_flag(const unsigned* p, unsigned target) {
  int it = 0;
  while ((int)(ld_relaxed(p) - target) < 0 && ++it < (1 << 20)) {}
  fence_acquire();
}
__device__ __forceinline__ void signal_release(unsigned* p) {
  asm volatile("red.release.gpu.global.add.u32 [%0], 1;" :: "l"(p) : "memory");
}
template <int ID, int N> __device__ __forceinline__ void bar_arrive() { asm volatile("bar.arrive %0, %1;" :: "n"(ID), "n"(N) : "memory"); }
template <int ID, int N> __device__ __forceinline__ void bar_sync() { asm volatile("bar.sync %0, %1;" :: "n"(ID), "n"(N) : "memory"); }
__device__ __forceinline__ void bar_wg(int wg) { asm volatile("bar.sync %0, 128;" :: "r"(2 + wg) : "memory"); }
__device__ __forceinline__ void cluster_sync() {
  asm volatile("barrier.cluster.arrive.relaxed.aligned;\nbarrier.cluster.wait.aligned;" ::: "memory");
}
__device__ __forceinline__ void cluster_wait() { asm volatile("barrier.cluster.wait.acquire.aligned;" ::: "memory"); }
enum { BAR_X1 = 7, BAR_WF = 8  , BAR_SKEW = 10 };

__device__ __forceinline__ void wgmma_fence() { asm volatile("wgmma.fence.sync.aligned;" ::: "memory"); }
__device__ __forceinline__ void wgmma_commit() { asm volatile("wgmma.commit_group.sync.aligned;" ::: "memory"); }
template <int N> __device__ __forceinline__ void wgmma_wait() { asm volatile("wgmma.wait_group.sync.aligned %0;" :: "n"(N) : "memory"); }

template <int scale_d, int tnsp_b = 1> __device__ __forceinline__ void wgmma_n192(float* d, uint64_t descA, uint64_t descB) {
  asm volatile("{\n.reg .pred p;\nsetp.ne.b32 p, %98, 0;\n"
               "wgmma.mma_async.sync.aligned.m64n192k16.f32.bf16.bf16 {%0,%1,%2,%3,%4,%5,%6,%7,%8,%9,%10,%11,%12,%13,%14,%15,%16,%17,%18,%19,%20,%21,%22,%23,%24,%25,%26,%27,%28,%29,%30,%31,%32,%33,%34,%35,%36,%37,%38,%39,%40,%41,%42,%43,%44,%45,%46,%47,%48,%49,%50,%51,%52,%53,%54,%55,%56,%57,%58,%59,%60,%61,%62,%63,%64,%65,%66,%67,%68,%69,%70,%71,%72,%73,%74,%75,%76,%77,%78,%79,%80,%81,%82,%83,%84,%85,%86,%87,%88,%89,%90,%91,%92,%93,%94,%95}, %96, %97, p, 1, 1, 0, %99;\n}\n"
               : "+f"(d[0]), "+f"(d[1]), "+f"(d[2]), "+f"(d[3]), "+f"(d[4]), "+f"(d[5]), "+f"(d[6]), "+f"(d[7]), "+f"(d[8]), "+f"(d[9]), "+f"(d[10]), "+f"(d[11]), "+f"(d[12]), "+f"(d[13]), "+f"(d[14]), "+f"(d[15]), "+f"(d[16]), "+f"(d[17]), "+f"(d[18]), "+f"(d[19]), "+f"(d[20]), "+f"(d[21]), "+f"(d[22]), "+f"(d[23]), "+f"(d[24]), "+f"(d[25]), "+f"(d[26]), "+f"(d[27]), "+f"(d[28]), "+f"(d[29]), "+f"(d[30]), "+f"(d[31]), "+f"(d[32]), "+f"(d[33]), "+f"(d[34]), "+f"(d[35]), "+f"(d[36]), "+f"(d[37]), "+f"(d[38]), "+f"(d[39]), "+f"(d[40]), "+f"(d[41]), "+f"(d[42]), "+f"(d[43]), "+f"(d[44]), "+f"(d[45]), "+f"(d[46]), "+f"(d[47]), "+f"(d[48]), "+f"(d[49]), "+f"(d[50]), "+f"(d[51]), "+f"(d[52]), "+f"(d[53]), "+f"(d[54]), "+f"(d[55]), "+f"(d[56]), "+f"(d[57]), "+f"(d[58]), "+f"(d[59]), "+f"(d[60]), "+f"(d[61]), "+f"(d[62]), "+f"(d[63]), "+f"(d[64]), "+f"(d[65]), "+f"(d[66]), "+f"(d[67]), "+f"(d[68]), "+f"(d[69]), "+f"(d[70]), "+f"(d[71]), "+f"(d[72]), "+f"(d[73]), "+f"(d[74]), "+f"(d[75]), "+f"(d[76]), "+f"(d[77]), "+f"(d[78]), "+f"(d[79]), "+f"(d[80]), "+f"(d[81]), "+f"(d[82]), "+f"(d[83]), "+f"(d[84]), "+f"(d[85]), "+f"(d[86]), "+f"(d[87]), "+f"(d[88]), "+f"(d[89]), "+f"(d[90]), "+f"(d[91]), "+f"(d[92]), "+f"(d[93]), "+f"(d[94]), "+f"(d[95])
               : "l"(descA), "l"(descB), "n"(scale_d), "n"(tnsp_b));
}
template <int scale_d> __device__ __forceinline__ void wgmma4_n192(float* d, uint32_t da, uint32_t db) {
#define R_ "{%0,%1,%2,%3,%4,%5,%6,%7,%8,%9,%10,%11,%12,%13,%14,%15,%16,%17,%18,%19,%20,%21,%22,%23,%24,%25,%26,%27,%28,%29,%30,%31,%32,%33,%34,%35,%36,%37,%38,%39,%40,%41,%42,%43,%44,%45,%46,%47,%48,%49,%50,%51,%52,%53,%54,%55,%56,%57,%58,%59,%60,%61,%62,%63,%64,%65,%66,%67,%68,%69,%70,%71,%72,%73,%74,%75,%76,%77,%78,%79,%80,%81,%82,%83,%84,%85,%86,%87,%88,%89,%90,%91,%92,%93,%94,%95}"
  asm volatile("{\n.reg .pred p, q;\n.reg .b64 a, b;\nsetp.ne.b32 p, %98, 0;\nsetp.eq.b32 q, 0, 0;\nmov.b64 a, {%96, 0x40000040};\nmov.b64 b, {%97, 0x40000040};\n"
               "wgmma.mma_async.sync.aligned.m64n192k16.f32.bf16.bf16 " R_ ", a, b, p, 1, 1, 0, 1;\nadd.s64 a, a, 2;\nadd.s64 b, b, 128;\n"
               "wgmma.mma_async.sync.aligned.m64n192k16.f32.bf16.bf16 " R_ ", a, b, q, 1, 1, 0, 1;\nadd.s64 a, a, 2;\nadd.s64 b, b, 128;\n"
               "wgmma.mma_async.sync.aligned.m64n192k16.f32.bf16.bf16 " R_ ", a, b, q, 1, 1, 0, 1;\nadd.s64 a, a, 2;\nadd.s64 b, b, 128;\n"
               "wgmma.mma_async.sync.aligned.m64n192k16.f32.bf16.bf16 " R_ ", a, b, q, 1, 1, 0, 1;\n}\n"
               : "+f"(d[0]), "+f"(d[1]), "+f"(d[2]), "+f"(d[3]), "+f"(d[4]), "+f"(d[5]), "+f"(d[6]), "+f"(d[7]), "+f"(d[8]), "+f"(d[9]), "+f"(d[10]), "+f"(d[11]), "+f"(d[12]), "+f"(d[13]), "+f"(d[14]), "+f"(d[15]), "+f"(d[16]), "+f"(d[17]), "+f"(d[18]), "+f"(d[19]), "+f"(d[20]), "+f"(d[21]), "+f"(d[22]), "+f"(d[23]), "+f"(d[24]), "+f"(d[25]), "+f"(d[26]), "+f"(d[27]), "+f"(d[28]), "+f"(d[29]), "+f"(d[30]), "+f"(d[31]), "+f"(d[32]), "+f"(d[33]), "+f"(d[34]), "+f"(d[35]), "+f"(d[36]), "+f"(d[37]), "+f"(d[38]), "+f"(d[39]), "+f"(d[40]), "+f"(d[41]), "+f"(d[42]), "+f"(d[43]), "+f"(d[44]), "+f"(d[45]), "+f"(d[46]), "+f"(d[47]), "+f"(d[48]), "+f"(d[49]), "+f"(d[50]), "+f"(d[51]), "+f"(d[52]), "+f"(d[53]), "+f"(d[54]), "+f"(d[55]), "+f"(d[56]), "+f"(d[57]), "+f"(d[58]), "+f"(d[59]), "+f"(d[60]), "+f"(d[61]), "+f"(d[62]), "+f"(d[63]), "+f"(d[64]), "+f"(d[65]), "+f"(d[66]), "+f"(d[67]), "+f"(d[68]), "+f"(d[69]), "+f"(d[70]), "+f"(d[71]), "+f"(d[72]), "+f"(d[73]), "+f"(d[74]), "+f"(d[75]), "+f"(d[76]), "+f"(d[77]), "+f"(d[78]), "+f"(d[79]), "+f"(d[80]), "+f"(d[81]), "+f"(d[82]), "+f"(d[83]), "+f"(d[84]), "+f"(d[85]), "+f"(d[86]), "+f"(d[87]), "+f"(d[88]), "+f"(d[89]), "+f"(d[90]), "+f"(d[91]), "+f"(d[92]), "+f"(d[93]), "+f"(d[94]), "+f"(d[95])
               : "r"(da), "r"(db), "n"(scale_d));
#undef R_
}
template <int scale_d> __device__ __forceinline__ void wgmma4_n128(float* d, uint32_t da, uint32_t db) {
#define R_ "{%0,%1,%2,%3,%4,%5,%6,%7,%8,%9,%10,%11,%12,%13,%14,%15,%16,%17,%18,%19,%20,%21,%22,%23,%24,%25,%26,%27,%28,%29,%30,%31,%32,%33,%34,%35,%36,%37,%38,%39,%40,%41,%42,%43,%44,%45,%46,%47,%48,%49,%50,%51,%52,%53,%54,%55,%56,%57,%58,%59,%60,%61,%62,%63}"
  asm volatile("{\n.reg .pred p, q;\n.reg .b64 a, b;\nsetp.ne.b32 p, %66, 0;\nsetp.eq.b32 q, 0, 0;\nmov.b64 a, {%64, 0x40000040};\nmov.b64 b, {%65, 0x40000040};\n"
               "wgmma.mma_async.sync.aligned.m64n128k16.f32.bf16.bf16 " R_ ", a, b, p, 1, 1, 0, 1;\nadd.s64 a, a, 2;\nadd.s64 b, b, 128;\n"
               "wgmma.mma_async.sync.aligned.m64n128k16.f32.bf16.bf16 " R_ ", a, b, q, 1, 1, 0, 1;\nadd.s64 a, a, 2;\nadd.s64 b, b, 128;\n"
               "wgmma.mma_async.sync.aligned.m64n128k16.f32.bf16.bf16 " R_ ", a, b, q, 1, 1, 0, 1;\nadd.s64 a, a, 2;\nadd.s64 b, b, 128;\n"
               "wgmma.mma_async.sync.aligned.m64n128k16.f32.bf16.bf16 " R_ ", a, b, q, 1, 1, 0, 1;\n}\n"
               : "+f"(d[0]), "+f"(d[1]), "+f"(d[2]), "+f"(d[3]), "+f"(d[4]), "+f"(d[5]), "+f"(d[6]), "+f"(d[7]), "+f"(d[8]), "+f"(d[9]), "+f"(d[10]), "+f"(d[11]), "+f"(d[12]), "+f"(d[13]), "+f"(d[14]), "+f"(d[15]), "+f"(d[16]), "+f"(d[17]), "+f"(d[18]), "+f"(d[19]), "+f"(d[20]), "+f"(d[21]), "+f"(d[22]), "+f"(d[23]), "+f"(d[24]), "+f"(d[25]), "+f"(d[26]), "+f"(d[27]), "+f"(d[28]), "+f"(d[29]), "+f"(d[30]), "+f"(d[31]), "+f"(d[32]), "+f"(d[33]), "+f"(d[34]), "+f"(d[35]), "+f"(d[36]), "+f"(d[37]), "+f"(d[38]), "+f"(d[39]), "+f"(d[40]), "+f"(d[41]), "+f"(d[42]), "+f"(d[43]), "+f"(d[44]), "+f"(d[45]), "+f"(d[46]), "+f"(d[47]), "+f"(d[48]), "+f"(d[49]), "+f"(d[50]), "+f"(d[51]), "+f"(d[52]), "+f"(d[53]), "+f"(d[54]), "+f"(d[55]), "+f"(d[56]), "+f"(d[57]), "+f"(d[58]), "+f"(d[59]), "+f"(d[60]), "+f"(d[61]), "+f"(d[62]), "+f"(d[63])
               : "r"(da), "r"(db), "n"(scale_d));
#undef R_
}
template <int scale_d> __device__ __forceinline__ void wgmma_n32(float* d, uint64_t descA, uint64_t descB) {
  asm volatile("{\n.reg .pred p;\nsetp.ne.b32 p, %18, 0;\n"
               "wgmma.mma_async.sync.aligned.m64n32k16.f32.bf16.bf16 {%0,%1,%2,%3,%4,%5,%6,%7,%8,%9,%10,%11,%12,%13,%14,%15}, %16, %17, p, 1, 1, 0, 1;\n}\n"
               : "+f"(d[0]), "+f"(d[1]), "+f"(d[2]), "+f"(d[3]), "+f"(d[4]), "+f"(d[5]), "+f"(d[6]), "+f"(d[7]), "+f"(d[8]), "+f"(d[9]), "+f"(d[10]), "+f"(d[11]), "+f"(d[12]), "+f"(d[13]), "+f"(d[14]), "+f"(d[15])
               : "l"(descA), "l"(descB), "n"(scale_d));
}
template <int scale_d, int tnsp_a> __device__ __forceinline__ void wgmma_n40(float* d, uint64_t descA, uint64_t descB) {
  asm volatile("{\n.reg .pred p;\nsetp.ne.b32 p, %22, 0;\n"
               "wgmma.mma_async.sync.aligned.m64n40k16.f32.bf16.bf16 {%0,%1,%2,%3,%4,%5,%6,%7,%8,%9,%10,%11,%12,%13,%14,%15,%16,%17,%18,%19}, %20, %21, p, 1, 1, %23, 1;\n}\n"
               : "+f"(d[0]), "+f"(d[1]), "+f"(d[2]), "+f"(d[3]), "+f"(d[4]), "+f"(d[5]), "+f"(d[6]), "+f"(d[7]), "+f"(d[8]), "+f"(d[9]), "+f"(d[10]), "+f"(d[11]), "+f"(d[12]), "+f"(d[13]), "+f"(d[14]), "+f"(d[15]), "+f"(d[16]), "+f"(d[17]), "+f"(d[18]), "+f"(d[19])
               : "l"(descA), "l"(descB), "n"(scale_d), "n"(tnsp_a));
}
template <int scale_d> __device__ __forceinline__ void wgmma_n40_rs(float* d, const uint32_t* a, uint64_t descB) {
  asm volatile("{\n.reg .pred p;\nsetp.ne.b32 p, %25, 0;\n"
               "wgmma.mma_async.sync.aligned.m64n40k16.f32.bf16.bf16 {%0,%1,%2,%3,%4,%5,%6,%7,%8,%9,%10,%11,%12,%13,%14,%15,%16,%17,%18,%19}, {%20,%21,%22,%23}, %24, p, 1, 1, 1;\n}\n"
               : "+f"(d[0]), "+f"(d[1]), "+f"(d[2]), "+f"(d[3]), "+f"(d[4]), "+f"(d[5]), "+f"(d[6]), "+f"(d[7]), "+f"(d[8]), "+f"(d[9]), "+f"(d[10]), "+f"(d[11]), "+f"(d[12]), "+f"(d[13]), "+f"(d[14]), "+f"(d[15]), "+f"(d[16]), "+f"(d[17]), "+f"(d[18]), "+f"(d[19])
               : "r"(a[0]), "r"(a[1]), "r"(a[2]), "r"(a[3]), "l"(descB), "n"(scale_d));
}
__device__ __forceinline__ void wgmma_copy(float* d, uint32_t da, uint64_t descB) {
  asm volatile("{\n.reg .pred p;\n.reg .b64 a;\nsetp.ne.b32 p, 0, 0;\nmov.b64 a, {%64, 0x40000040};\n"
               "wgmma.mma_async.sync.aligned.m64n16k16.f32.bf16.bf16 {%0,%1,%2,%3,%4,%5,%6,%7}, a, %65, p, 1, 1, 0, 0;\nadd.s64 a, a, 2;\n"
               "wgmma.mma_async.sync.aligned.m64n16k16.f32.bf16.bf16 {%8,%9,%10,%11,%12,%13,%14,%15}, a, %65, p, 1, 1, 0, 0;\nadd.s64 a, a, 2;\n"
               "wgmma.mma_async.sync.aligned.m64n16k16.f32.bf16.bf16 {%16,%17,%18,%19,%20,%21,%22,%23}, a, %65, p, 1, 1, 0, 0;\nadd.s64 a, a, 2;\n"
               "wgmma.mma_async.sync.aligned.m64n16k16.f32.bf16.bf16 {%24,%25,%26,%27,%28,%29,%30,%31}, a, %65, p, 1, 1, 0, 0;\nadd.s64 a, a, 1018;\n"
               "wgmma.mma_async.sync.aligned.m64n16k16.f32.bf16.bf16 {%32,%33,%34,%35,%36,%37,%38,%39}, a, %65, p, 1, 1, 0, 0;\nadd.s64 a, a, 2;\n"
               "wgmma.mma_async.sync.aligned.m64n16k16.f32.bf16.bf16 {%40,%41,%42,%43,%44,%45,%46,%47}, a, %65, p, 1, 1, 0, 0;\nadd.s64 a, a, 2;\n"
               "wgmma.mma_async.sync.aligned.m64n16k16.f32.bf16.bf16 {%48,%49,%50,%51,%52,%53,%54,%55}, a, %65, p, 1, 1, 0, 0;\nadd.s64 a, a, 2;\n"
               "wgmma.mma_async.sync.aligned.m64n16k16.f32.bf16.bf16 {%56,%57,%58,%59,%60,%61,%62,%63}, a, %65, p, 1, 1, 0, 0;\n"
               "}\n"
               : "+f"(d[0]), "+f"(d[1]), "+f"(d[2]), "+f"(d[3]), "+f"(d[4]), "+f"(d[5]), "+f"(d[6]), "+f"(d[7]), "+f"(d[8]), "+f"(d[9]), "+f"(d[10]), "+f"(d[11]), "+f"(d[12]), "+f"(d[13]), "+f"(d[14]), "+f"(d[15]), "+f"(d[16]), "+f"(d[17]), "+f"(d[18]), "+f"(d[19]), "+f"(d[20]), "+f"(d[21]), "+f"(d[22]), "+f"(d[23]), "+f"(d[24]), "+f"(d[25]), "+f"(d[26]), "+f"(d[27]), "+f"(d[28]), "+f"(d[29]), "+f"(d[30]), "+f"(d[31]), "+f"(d[32]), "+f"(d[33]), "+f"(d[34]), "+f"(d[35]), "+f"(d[36]), "+f"(d[37]), "+f"(d[38]), "+f"(d[39]), "+f"(d[40]), "+f"(d[41]), "+f"(d[42]), "+f"(d[43]), "+f"(d[44]), "+f"(d[45]), "+f"(d[46]), "+f"(d[47]), "+f"(d[48]), "+f"(d[49]), "+f"(d[50]), "+f"(d[51]), "+f"(d[52]), "+f"(d[53]), "+f"(d[54]), "+f"(d[55]), "+f"(d[56]), "+f"(d[57]), "+f"(d[58]), "+f"(d[59]), "+f"(d[60]), "+f"(d[61]), "+f"(d[62]), "+f"(d[63])
               : "r"(da), "l"(descB));
}
__device__ __forceinline__ uint64_t make_desc(uint32_t addr, uint32_t lbo_bytes, uint32_t sbo_bytes) {
  return (uint64_t)((addr & 0x3FFFF) >> 4) | ((uint64_t)(lbo_bytes >> 4) << 16) | ((uint64_t)(sbo_bytes >> 4) << 32) | (1ull << 62);
}

__device__ __forceinline__ void ldsm_x4(uint32_t addr, uint32_t& r0, uint32_t& r1, uint32_t& r2, uint32_t& r3) {
  asm volatile("ldmatrix.sync.aligned.m8n8.x4.shared.b16 {%0,%1,%2,%3}, [%4];" : "=r"(r0), "=r"(r1), "=r"(r2), "=r"(r3) : "r"(addr) : "memory");
}
__device__ __forceinline__ void ldsm_x4_t(uint32_t addr, uint32_t& r0, uint32_t& r1, uint32_t& r2, uint32_t& r3) {
  asm volatile("ldmatrix.sync.aligned.m8n8.x4.trans.shared.b16 {%0,%1,%2,%3}, [%4];" : "=r"(r0), "=r"(r1), "=r"(r2), "=r"(r3) : "r"(addr) : "memory");
}
__device__ __forceinline__ void stsm_x4(uint32_t addr, uint32_t r0, uint32_t r1, uint32_t r2, uint32_t r3) {
  asm volatile("stmatrix.sync.aligned.m8n8.x4.shared.b16 [%0], {%1,%2,%3,%4};" :: "r"(addr), "r"(r0), "r"(r1), "r"(r2), "r"(r3) : "memory");
}
__device__ __forceinline__ void sts128(uint32_t addr, uint32_t a, uint32_t b, uint32_t c, uint32_t d) {
  asm volatile("st.shared.v4.u32 [%0], {%1,%2,%3,%4};" :: "r"(addr), "r"(a), "r"(b), "r"(c), "r"(d) : "memory");
}
__device__ __forceinline__ float lds32f(uint32_t addr) {
  float v;
  asm volatile("ld.shared.f32 %0, [%1];" : "=f"(v) : "r"(addr) : "memory");
  return v;
}
__device__ __forceinline__ void sts32f(uint32_t addr, float a) {
  asm volatile("st.shared.f32 [%0], %1;" :: "r"(addr), "f"(a) : "memory");
}
__device__ __forceinline__ void mma_bf16(float (&c)[4], uint32_t a0, uint32_t a1, uint32_t a2, uint32_t a3, uint32_t b0, uint32_t b1) {
  asm volatile("mma.sync.aligned.m16n8k16.row.col.f32.bf16.bf16.f32 {%0,%1,%2,%3}, {%4,%5,%6,%7}, {%8,%9}, {%0,%1,%2,%3};"
               : "+f"(c[0]), "+f"(c[1]), "+f"(c[2]), "+f"(c[3]) : "r"(a0), "r"(a1), "r"(a2), "r"(a3), "r"(b0), "r"(b1));
}
__device__ __forceinline__ void mma_bf16_z(float (&c)[4], uint32_t a0, uint32_t a1, uint32_t a2, uint32_t a3, uint32_t b0, uint32_t b1) {
  asm volatile("mma.sync.aligned.m16n8k16.row.col.f32.bf16.bf16.f32 {%0,%1,%2,%3}, {%4,%5,%6,%7}, {%8,%9}, {%10,%10,%10,%10};"
               : "=f"(c[0]), "=f"(c[1]), "=f"(c[2]), "=f"(c[3]) : "r"(a0), "r"(a1), "r"(a2), "r"(a3), "r"(b0), "r"(b1), "f"(0.f));
}
__device__ __forceinline__ uint32_t movm_t(uint32_t v) {
  uint32_t r;
  asm volatile("movmatrix.sync.aligned.m8n8.trans.b16 %0, %1;" : "=r"(r) : "r"(v));
  return r;
}
__device__ __forceinline__ uint32_t pack_bf16(float lo, float hi) {
  uint32_t r;
  asm("cvt.rn.bf16x2.f32 %0, %1, %2;" : "=r"(r) : "f"(hi), "f"(lo));
  return r;
}
__device__ __forceinline__ float bf_lo(uint32_t v) { return __uint_as_float(v << 16); }
__device__ __forceinline__ float bf_hi(uint32_t v) { return __uint_as_float(v & 0xFFFF0000u); }
__device__ __forceinline__ void split3(float x, uint32_t& h, uint32_t& m, uint32_t& l) {
  h = pack_bf16(x, 0.f); x -= bf_lo(h);
  m = pack_bf16(x, 0.f); x -= bf_lo(m);
  l = pack_bf16(x, 0.f);
}
__device__ __forceinline__ float ex2(float x) { float r; asm("ex2.approx.ftz.f32 %0, %1;" : "=f"(r) : "f"(x)); return r; }
__device__ __forceinline__ float rcp_fast(float x) { float r; asm("rcp.approx.ftz.f32 %0, %1;" : "=f"(r) : "f"(x)); return r; }
__device__ __forceinline__ void red_v4(float* p, float a, float b, float c, float d) {
  asm volatile("red.global.add.v4.f32 [%0], {%1, %2, %3, %4};" :: "l"(p), "f"(a), "f"(b), "f"(c), "f"(d) : "memory");
}
__device__ __forceinline__ uint4 ld_ll(const uint4* p) {
  uint4 v;
  asm volatile("{\n.reg .b64 a, b;\nld.relaxed.gpu.global.v2.b64 {a, b}, [%4];\nmov.b64 {%0, %1}, a;\nmov.b64 {%2, %3}, b;\n}\n"
               : "=r"(v.x), "=r"(v.y), "=r"(v.z), "=r"(v.w) : "l"(p) : "memory");
  return v;
}
__device__ __forceinline__ void st_b64(uint2* p, uint32_t a, uint32_t b) {
  asm volatile("{\n.reg .b64 v;\nmov.b64 v, {%1, %2};\nst.relaxed.gpu.global.b64 [%0], v;\n}\n" :: "l"(p), "r"(a), "r"(b) : "memory");
}
__device__ __forceinline__ void st_b128(uint4* p, uint32_t a, uint32_t b, uint32_t c, uint32_t d) {
  asm volatile("{\n.reg .b128 v;\nmov.b128 v, {%1, %2, %3, %4};\nst.relaxed.gpu.global.b128 [%0], v;\n}\n" :: "l"(p), "r"(a), "r"(b), "r"(c), "r"(d) : "memory");
}
__device__ __forceinline__ uint4 ld_b128(const uint4* p) {
  uint4 v;
  asm volatile("{\n.reg .b128 v;\nld.relaxed.gpu.global.b128 v, [%4];\nmov.b128 {%0, %1, %2, %3}, v;\n}\n" : "=r"(v.x), "=r"(v.y), "=r"(v.z), "=r"(v.w) : "l"(p) : "memory");
  return v;
}

constexpr float LOG2E = 1.4426950408889634f;

struct Params {
  const __nv_bfloat16* x0;
  const __nv_bfloat16* wA_qkv;
  const __nv_bfloat16* wA_o;
  const __nv_bfloat16* wB_qkv;
  const __nv_bfloat16* wB_phi;
  const __nv_bfloat16* wB_o;
  __nv_bfloat16* out;
};

#define ACC_DEF(d, n) _Pragma("unroll") for (int i_ = 0; i_ < (n); i_++) asm volatile("" : "=f"(d[i_]))
#define ACC_FENCE(d, n) _Pragma("unroll") for (int i_ = 0; i_ < (n); i_++) asm volatile("" : "+f"(d[i_]) :: "memory")
#define PIN(a, n) _Pragma("unroll") for (int i_ = 0; i_ < (n); i_++) asm volatile("" : "+f"((a)[i_]))
#define PINU(a, n) _Pragma("unroll") for (int i_ = 0; i_ < (n); i_++) asm volatile("" : "+r"((a)[i_]))

#define V_ADDR(p0) uint32_t va_[2] = {(p0) + (srowoff >> 1) + (lhi ^ lsw2), (p0) + (srowoff >> 1) + ((32 + lhi) ^ lsw2)}
#define STAGE_V(acc) { \
    _Pragma("unroll") for (int j_ = 0; j_ < 4; j_++) { \
      const float* a_ = (acc) + j_ * 8; \
      stsm_x4(va_[j_ & 1] + (j_ >> 1) * 8192, \
              pack_bf16(rs0 * a_[0], rs0 * a_[1]), pack_bf16(rs1 * a_[2], rs1 * a_[3]), pack_bf16(rs0 * a_[4], rs0 * a_[5]), pack_bf16(rs1 * a_[6], rs1 * a_[7])); } }
#define FRAG(dst, acc, TR, grp) { \
    _Pragma("unroll") for (int i_ = 0; i_ < 16; i_++) { \
      const float r_ = (i_ & 1) ? rs1 : rs0; \
      const uint32_t w_ = pack_bf16(r_ * (acc)[2 * i_], r_ * (acc)[2 * i_ + 1]); \
      if (TR) (dst)[i_] = movm_t(w_); else (dst)[(i_ & 12) + (i_ & 1) * 2 + ((i_ >> 1) & 1)] = w_; } \
    if (warp == 7 && mm < 15) { \
      _Pragma("unroll") for (int j_ = 0; j_ < 4; j_++) \
        st_b128(g_halo + (size_t)(mm * 8 + jj) * 512 + ((grp) * 4 + j_) * 32 + lane, ((dst)[j_ * 4] & ~1u) | H_BIT(l), (dst)[j_ * 4 + 1], (dst)[j_ * 4 + 2], (dst)[j_ * 4 + 3]); } \
    PINU(dst, 16); }
#define FRAG_PUT(src, slot) if (warp < 7) { _Pragma("unroll") for (int j_ = 0; j_ < 4; j_++) \
      sts128(sbase + (slot) * SLOT + 2048 + warp * 2048 + j_ * 512 + lane * 16, (src)[j_ * 4], (src)[j_ * 4 + 1], (src)[j_ * 4 + 2], (src)[j_ * 4 + 3]); }
#define FRAG_GET(dst, slot) { _Pragma("unroll") for (int j_ = 0; j_ < 4; j_++) \
      asm volatile("ld.shared.v4.u32 {%0, %1, %2, %3}, [%4];" : "=r"((dst)[j_ * 4]), "=r"((dst)[j_ * 4 + 1]), "=r"((dst)[j_ * 4 + 2]), "=r"((dst)[j_ * 4 + 3]) \
                   : "r"(sbase + (slot) * SLOT + warp * 2048 + j_ * 512 + lane * 16) : "memory"); }
#define RW(j) (((j) >> 1) * 4 + ((j) & 1))
template <int POS> __device__ __forceinline__ float exps16_(float* o, const float* p) {
  float s[4];
#pragma unroll
  for (int j = 0; j < 16; j++) { o[j] = ex2(POS ? p[RW(j)] : -p[RW(j)]); if (j < 4) s[j] = o[j]; else s[j & 3] += o[j]; }
  const float r = (s[0] + s[1]) + (s[2] + s[3]);
  return r + __shfl_xor_sync(0xffffffffu, r, 1);
}
template <int POS> __device__ __forceinline__ void exps16_fix(float* o, const float* p, float& sum) {
  if (__builtin_expect(__any_sync(0xffffffffu, !(sum > SUMLO && sum < SUMHI)), 0)) {
    float m = p[0], q[32];
#pragma unroll
    for (int j = 1; j < 16; j++) m = POS ? fmaxf(m, p[RW(j)]) : fminf(m, p[RW(j)]);
    const float x = __shfl_xor_sync(0xffffffffu, m, 1);
    m = POS ? fmaxf(m, x) : fminf(m, x);
#pragma unroll
    for (int j = 0; j < 16; j++) q[RW(j)] = p[RW(j)] - m;
    sum = exps16_<POS>(o, q);
  }
}
__device__ __forceinline__ void store16(const float* e, float sum, uint32_t dst, uint32_t dsw, int c0) {
  const float inv = rcp_fast(sum);
#pragma unroll
  for (int j = 0; j < 2; j++)
    sts128(dst + (((c0 + j) << 4) ^ dsw), pack_bf16(e[j * 8] * inv, e[j * 8 + 1] * inv), pack_bf16(e[j * 8 + 2] * inv, e[j * 8 + 3] * inv),
           pack_bf16(e[j * 8 + 4] * inv, e[j * 8 + 5] * inv), pack_bf16(e[j * 8 + 6] * inv, e[j * 8 + 7] * inv));
}
template <int POS> __device__ __forceinline__ void expp16(uint32_t* o, float* p) {
  {
#pragma unroll
    for (int r = 0; r < 4; r += 2) {
      float m = p[r];
#pragma unroll
      for (int j = 1; j < 8; j++) m = POS ? fmaxf(m, p[r + RW(j)]) : fminf(m, p[r + RW(j)]);
#pragma unroll
      for (int s = 1; s <= 2; s <<= 1) { const float x = __shfl_xor_sync(0xffffffffu, m, s); m = POS ? fmaxf(m, x) : fminf(m, x); }
#pragma unroll
      for (int j = 0; j < 8; j++) p[r + RW(j)] -= m;
    }
  }
#pragma unroll
  for (int j = 0; j < 8; j++) o[j] = pack_bf16(ex2(POS ? p[2 * j] : -p[2 * j]), ex2(POS ? p[2 * j + 1] : -p[2 * j + 1]));
}
__device__ __forceinline__ void scale32(float* o, const float* p, float c0, float c1) {
#pragma unroll
  for (int i = 0; i < 32; i++) asm volatile("mul.f32 %0, %1, %2;" : "=f"(o[i]) : "f"(p[i]), "f"((i & 2) ? c1 : c0));
}
__device__ __forceinline__ bool any_big(const float* p) {
  float m[4];
#pragma unroll
  for (int i = 0; i < 32; i++) m[i >> 3] = (i & 7) ? fmaf(p[i], p[i], m[i >> 3]) : p[i] * p[i];
  return __any_sync(0xffffffffu, !(fmaxf(fmaxf(m[0], m[1]), fmaxf(m[2], m[3])) < BIGLIM));
}
__device__ __forceinline__ void phiq_a(float* p, bool big) {
  if (__builtin_expect(!big, 1)) {
#pragma unroll
    for (int j = 0; j < 16; j++) p[j] = ex2(p[j]);
  }
}
template <int NEXT> __device__ __forceinline__ void phiq_b(uint32_t* o, float* p, bool big) {
  if (__builtin_expect(big, 0)) {
    expp16<0>(o, p); expp16<1>(o + 8, p);
  } else {
    if (NEXT) phiq_a(p + 16, false);
#pragma unroll
    for (int j = 0; j < 4; j++) {
      const float a = p[4 * j], b = p[4 * j + 1], c = p[4 * j + 2], d = p[4 * j + 3];
      const float ab = a * b, cd = c * d, r = rcp_fast(ab * cd), x = r * cd, y = r * ab;
      o[2 * j] = pack_bf16(x * b, x * a); o[2 * j + 1] = pack_bf16(y * d, y * c);
      o[8 + 2 * j] = pack_bf16(a, b); o[9 + 2 * j] = pack_bf16(c, d);
    }
  }
}
#define SCHED_FENCE() asm volatile("pmevent 0;" ::: "memory")

__global__ void __cluster_dims__(2, 1, 1) __launch_bounds__(384, 1)
mega_kernel(const __grid_constant__ CUtensorMap tm_x0, const __grid_constant__ CUtensorMap tm_xo, const __grid_constant__ CUtensorMap tm_os,
            const __grid_constant__ CUtensorMap tm_o, const __grid_constant__ CUtensorMap tm_wf,
            const __grid_constant__ CUtensorMap tm_wqA, const __grid_constant__ CUtensorMap tm_wqB,
            const __grid_constant__ CUtensorMap tm_woA, const __grid_constant__ CUtensorMap tm_woB,
            const __grid_constant__ CUtensorMap tm_phi, const Params prm) {
  extern __shared__ __align__(1024) uint8_t smem_raw[];
  const uint32_t sbase = smem_u32(smem_raw);
  const uint32_t bar_full = sbase + OFF_BAR;
  const uint32_t bar_done = bar_full + 384;
  const uint32_t bar_stat = bar_full + 768, bar_stat2 = bar_full + 776, bar_epi = bar_full + 784, bar_phi = bar_full + 936  , bar_halo = bar_full + 904  ;
  const uint32_t bar_xr = bar_full + 800, bar_lx = bar_full + 808, bar_stg = bar_full + 832;
  const uint32_t bar_chk = bar_full + 848;

  const int warp = __shfl_sync(0xffffffffu, threadIdx.x >> 5, 0), lane = threadIdx.x & 31;
  const uint32_t bar_kx = sbase + OFF_ID + 384 + warp * 8;
  uint32_t rank;
  asm volatile("mov.u32 %0, %%cluster_ctarank;" : "=r"(rank));
  const int aux = (int)blockIdx.x - NMAIN, tp = (int)(blockIdx.x >> 1) - 4;
  const int gp = tp < 0 ? 0 : (tp < 32 ? tp & 7 : 1 + (tp - 32) % 7), me = tp < 0 ? tp + 8 : (tp < 32 ? tp >> 3 : 4 + (tp - 32) / 7);
  const int jj = me, cc = gp;
  const int cta = aux >= 0 ? -1 : (cc * 8 + jj) * 2 + (int)rank;
  const int mm = cc * 2 + (int)rank;

#define LOAD_EPOCH() const unsigned epoch = ld_relaxed(&g_flags.epoch.v), ep1 = epoch + 1; (void)epoch
  int budget = 1 << 22;

  if (cta >= 0) {
    if (warp >= 8 && warp < 8 + EARLY && elect_one()) {
      const int u = warp - 8;
      const uint32_t fb = bar_full + u * 8;
      mbar_init(fb, 1);
      asm volatile("fence.mbarrier_init.release.cluster;" ::: "memory");
      fence_proxy_async_smem();
      mbar_expect_tx(fb, QST + SLOT);
      if (u) __nanosleep(STAG2);
      tma_load_2d(sbase + OFF_S + u * SLOT, &tm_x0, fb, jj * 128 + u * 64, mm * 128);
#pragma unroll
      for (int i = 0; i < 6; i++) tma_load_2d(sbase + u * QST + i * 4096, &tm_wqA, fb, jj * 128 + (i >> 1) * 1024, jj * 128 + u * 64 + (i & 1) * 32);
      if (u == 0) PROFT(472);
    }
    __syncwarp();
    {
      const int tx = threadIdx.x;
      const __nv_bfloat16* pf = (tx < 128) ? prm.x0 + (size_t)(mm * 128 + tx) * D_MODEL + jj * 128
                                           : prm.wA_qkv + (size_t)(jj * 128 + (tx & 63)) * 3072 + ((tx - 128) >> 6) * 1024 + jj * 128 + rank * 64;
      if (tx < 320) asm volatile("prefetch.global.L2 [%0];" :: "l"(pf));
      else if (tx == 320) prefetch_tmap(&tm_x0);
      else if (tx == 352) prefetch_tmap(&tm_wqA);
      else if (tx == 383) asm volatile("prefetch.global.L2 [%0];" :: "l"(&g_flags.epoch.v));
    }
    if (elect_one()) {
#pragma unroll
      for (int i = 0; i < 4; i++) {
        const int u = warp * 4 + i;
        if (u >= EARLY) mbar_init(bar_full + u * 8, ((u >= 4 && u < 11) || (u > 32 && u != 40)) ? 2 : 1); mbar_init(bar_done + u * 8, 16);
      }
      mbar_init(bar_stat + warp * 16, 0x111111181182ull >> (4 * warp) & 15);
      mbar_init(bar_stat + warp * 16 + 8, 0x111111121811ull >> (4 * warp) & 15);
      mbar_init(bar_chk + 112 + (warp & 7) * 8, 1);
      mbar_init(bar_kx, 1);
      asm volatile("fence.mbarrier_init.release.cluster;" ::: "memory");
    }
    __syncwarp();
    __syncthreads();
    asm volatile("barrier.cluster.arrive.relaxed.aligned;" ::: "memory");
  }

  if (cta < 0) {
    LOAD_EPOCH();
    const uint32_t buf = sbase + warp * SLOT, bar = sbase + OFF_BAR + warp * 16;
    const uint32_t lsw = (lane & 7) << 4, lhi = (lane >> 4) << 4, lrow = (lane & 15) * 128;
    const bool el = elect_one();
    if (el) {
      mbar_init(bar, 1); mbar_init(bar + 8, 1);
      asm volatile("fence.mbarrier_init.release.cluster;" ::: "memory");
    }
#pragma unroll 1
    for (int rd = 0; rd < (NLAYERS > 1 ? 5 : 2); rd++) {
      if (rd >= 2 && warp >= 8) break;
      const int tk = rd < 2 ? aux * 12 + warp : aux * 8 + warp;
      const int half = tk & 1;
      const int blk = rd < 2 ? (tk >> 1) * 2 + rd : (4 - rd) * 16 + (tk >> 1);
      const CUtensorMap* tm = rd < 2 ? &tm_wqA : (rd == 2 ? &tm_wqB : &tm_wf);
      const int j0 = (blk & 15) >> 1;
#define AUX_LOAD(n) { const uint32_t d_ = buf + ((n) & 1) * 8192, b_ = bar + ((n) & 1) * 8; const int r_ = kslice(j0, 2 * (n) + half) * 64; \
        mbar_expect_tx(b_, 8192); tma_load_2d(d_, tm, b_, blk * 64, r_); tma_load_2d(d_ + 4096, tm, b_, blk * 64, r_ + 32); }
      if (el) {
        if (rd == 3) { wait_flag(&g_flags.wfready[j0].v, ep1 * 16); fence_proxy_async_global(); }
        AUX_LOAD(0); AUX_LOAD(1);
      }
      __syncwarp();
      float cs[8][4];
#pragma unroll
      for (int i = 0; i < 8; i++) cs[i][0] = cs[i][1] = cs[i][2] = cs[i][3] = 0.f;
#pragma unroll 1
      for (int n = 0; n < 8; n++) {
        const uint32_t tb = buf + (n & 1) * 8192 + lrow;
        mbar_wait(bar + (n & 1) * 8, (n >> 1) & 1);
#pragma unroll
        for (int i = 0; i < 16; i++) {
          uint32_t b0, b1, b2, b3;
          ldsm_x4_t(tb + (i >> 2) * 2048 + (((i & 3) * 32 + lhi) ^ lsw), b0, b1, b2, b3);
          mma_bf16(cs[2 * (i & 3)], 0x3F803F80u, 0x3F803F80u, 0x3F803F80u, 0x3F803F80u, b0, b1);
          mma_bf16(cs[2 * (i & 3) + 1], 0x3F803F80u, 0x3F803F80u, 0x3F803F80u, 0x3F803F80u, b2, b3);
        }
        __syncwarp();
        if (el && n < 6) AUX_LOAD(n + 2);
        __syncwarp();
      }
      if (lane < 4) {
#pragma unroll
        for (int i = 0; i < 8; i++) st_b64(&g_colsum[rd >= 2][blk * 32 + i * 4 + lane][half], __float_as_uint(cs[i][0]), (__float_as_uint(cs[i][1]) & ~3u) | (ep1 & 3));
      }
      __syncwarp();
    }
  } else if (warp >= 8) {
    asm volatile("setmaxnreg.dec.sync.aligned.u32 40;");
    if (warp == 8) {
      const bool el = elect_one();
      cluster_wait();
      if (el) {
#pragma unroll 1
        for (int l = 0; l < NLAYERS; l++) {
          const uint32_t par = l & 1;
          const CUtensorMap* tqk = par ? &tm_wf : &tm_wqA;
          const CUtensorMap* tv = par ? &tm_wqB : &tm_wqA;
          const CUtensorMap* two = par ? &tm_woB : &tm_woA;
          if (l == 1) { LOAD_EPOCH(); wait_flag(&g_flags.wfready[jj].v, ep1 * 16); fence_proxy_async_global(); }
#pragma unroll 1
          for (int u = l ? 0 : EARLY; u < 32; u++) {
            if (u >= 4) mbar_wait_sl(bar_done + (u - 4) * 8, par);
            else if (l) mbar_wait_sl(bar_done + (43 + u + (u >> 1)) * 8, par ^ 1);
            else mbar_wait_sl(bar_full, 0);
            const uint32_t fb = bar_full + u * 8;
            const bool res = u < 11 || (u >= 18 && u < 22);
            mbar_expect_tx(fb, res ? QST : QST + SLOT);
            const int row = kslice(jj, u < 4 ? u & 1 : (u < 18 ? u - 2 : (u < 22 ? u - 6 : u - 20))) * 64 + (int)rank * 32;
            const int ps = u < 4 ? u >> 1 : (u >= 18), col = jj * 128 + ps * 64;
            const int c0 = par ? jj * 128 + (ps ? 0 : 1024) : col;
            const uint32_t dst = sbase + (u & 3) * QST + rank * 4096;
            tma_load_2d_mc(dst, tqk, fb, c0, row);
            tma_load_2d_mc(dst + 8192, tqk, fb, c0 + (par ? 64 : 1024), row);
            tma_load_2d_mc(dst + 16384, tv, fb, col + 2048, row);
            if (l == PRL && u >= PRU && u < PRU + 4) PROFT(473 + u - PRU);
          }
#pragma unroll 1
          for (int s = 0; s < 16; s++) {
            if (s < 5) { if (s != 2 && s != 4) mbar_wait_sl(bar_done + (28 + s) * 8, par); }
            else if (s != 14) mbar_wait_sl(bar_done + (27 + s - (s == 15)) * 8, par);
            const uint32_t fb = bar_full + (32 + s) * 8;
            mbar_expect_tx(fb, SLOT);
            tma_load_2d_mc(sbase + rank * 8192 + (uint32_t)((WO_BSLOT >> (4 * s)) & 15) * SLOT, two, fb, jj * 128 + (int)rank * 64, wslice(jj, s) * 64);
            const int ts = s + par;
            if (s >= 5 && ts < 8) {
              mbar_expect_tx(bar_chk - 8 + ts * 8, SLOT);
              tma_load_2d(sbase + (uint32_t)((WO_ASLOT(par) >> (4 * ts)) & 15) * SLOT, &tm_o, bar_chk - 8 + ts * 8, wslice(jj, ts) * 64, mm * 128);
            }
          }
        }
      }
      __syncwarp();
    } else if (warp == 9) {
      const bool el = elect_one();
      LOAD_EPOCH();
#pragma unroll 1
      for (int lp = 0; lp < 4 * NLAYERS; lp++) {
        const int l = lp >> 2, ph = lp & 3;
        if (ph == 3) continue;
        const uint32_t par = l & 1;
        const unsigned* pp = reinterpret_cast<const unsigned*>(g_obuf + (ph >> 1) * 64 + (size_t)(mm * 128 + (ph ? 0 : S_LEN) + ((lane & 7) | PROWS) * 16 + (jj & 1) * 8) * D_MODEL +
                                                               (jj >> 1) * 16 + srcb(jj, lane >> 3) * 128);
        const CUtensorMap* tm = lp ? &tm_o : &tm_x0;
        const int row = mm * 128 + ((ph || !l) ? 0 : S_LEN);
        const uint32_t bit = ph ? O_BIT(l) : X_BIT(l - 1);
        const uint32_t slots = ph ? (uint32_t)(WO_ASLOT(par) >> (ph * 32 - 28)) : 0x8769876u;
        const unsigned long long fr = ph == 0 ? XPACE : ph == 1 ? (par ? FRB : 0x35351F1Eull) : (par ? 0x27262524232232ull : 0x27262524233232ull);
        uint32_t no = (lp == 0 || (lp & 7) == 1) ? 0 : (ph == 1 ? NOB : (ph ? NO1 : NOX)), v0 = 0, v1 = 0;
        mbar_wait_sl(ph ? bar_done + ((uint32_t)fr & 63) * 8 : (l ? bar_done + 47 * 8 : bar_full), ph ? par : (l ? par ^ 1 : 0));
        if (el && ph) PROFT(324 + l * 16 + ph);
        __syncwarp();
        if (no && (ph == 1 ? SPD1 : (ph ? SPD2 : SPD0))) __nanosleep(ph == 1 ? SPD1 : (ph ? SPD2 : SPD0));
        if (no) { v0 = ld_relaxed(pp); __nanosleep(POLLGAP); v1 = ld_relaxed(pp); }
#pragma unroll 1
        for (int i = 0; i < (ph == 1 ? 4 + par : 7); i++, no >>= 8) {
#pragma unroll 1
          for (int it = 0; (no & 0xFF) && it < (1 << 18); it++) {
            no &= __ballot_sync(0xffffffffu, (v0 ^ bit) & 1) >> (8 * i);
            if (no) v0 = ld_relaxed(pp);
            if (!(no & 0xFF)) break;
            no &= __ballot_sync(0xffffffffu, (v1 ^ bit) & 1) >> (8 * i);
            if (no) v1 = ld_relaxed(pp);
          }
          if (ph || i >= XP0) mbar_wait_sl(bar_done + ((uint32_t)(fr >> (8 * i)) & 63) * 8, par);
          if (el) {
            if (i == 0) PROFT(320 + l * 16 + ph);
            const uint32_t cb = (lp ? bar_chk + (ph >> 1) * 112 : bar_full + 32) + i * 8;
            mbar_expect_tx(cb, SLOT);
            tma_load_2d(sbase + ((slots >> (4 * i)) & 15) * SLOT, tm, cb, srcb(jj, i) * 128 + (ph >> 1) * 64, row);
          }
          __syncwarp();
        }
        if (ph == 0 && el) {
          if (l) { wait_flag(&g_flags.xready[l][mm].v, ep1 * 8); fence_proxy_async_global(); }
#pragma unroll 1
          for (int u = 11; u < 34; u++) {
            if (u == 18) u = 22;
            mbar_wait_sl(bar_done + (u - 4) * 8, par);
            if (u == 32) mbar_expect_tx(bar_xr, 2 * SLOT);
            tma_load_2d(sbase + OFF_RA + (u & 3) * SLOT, tm, u < 32 ? bar_full + u * 8 : bar_xr, kslice(jj, u < 18 ? u - 2 : (u < 32 ? u - 20 : u - 32)) * 64, row);
          }
        }
        __syncwarp();
      }
      if (el && atomicAdd(&g_flags.done.v, 1) == ep1 * NMAIN - 1) asm volatile("st.relaxed.gpu.global.u32 [%0], %1;" :: "l"(&g_flags.epoch.v), "r"(ep1) : "memory");
      __syncwarp();
      cluster_wait();
    } else {
      const int hw = warp - 10;
      LOAD_EPOCH();
      const bool el = elect_one();
      cluster_wait();
      if (hw == 0) {
        mbar_wait_sl(bar_full + 8, 0);
        if (lane < 7) prefetch_tmap(lane == 0 ? &tm_os : lane == 1 ? &tm_o : lane == 2 ? &tm_wf : lane == 3 ? &tm_wqB : lane == 4 ? &tm_woA : lane == 5 ? &tm_woB : &tm_phi);
#pragma unroll 1
        for (int i = 0; i < (NLAYERS > 1 ? 9 : 0); i++) {
          if (i == 0 || i == 5) mbar_wait_sl(bar_done + (i ? FD1 : FD0) * 8, 0);
          if (el) {
            if (i == 0) { mbar_expect_tx(bar_phi, 2 * SLOT + 8192); tma_load_2d(sbase + OFF_PHI, &tm_phi, bar_phi, 0, jj * 128); }
            else tma_load_2d(sbase + (i > 4 ? 10 : 12) * SLOT - 4096 + i * 4096, &tm_wqB, bar_phi, (i > 4 ? 896 : 0) + jj * 128 + ((i - 1) >> 1) * 64, mm * 64 + (~i & 1) * 32);
          }
          __syncwarp();
          __nanosleep(PFGAP);
        }
      } else {
        if (lane < 24) {
          const uint32_t one = (lane & 8) ? 0u : 0x3F80u << ((lane & 1) * 16), w = (lane >> 1) & 3;
          sts128(sbase + OFF_ID + lane * 16, w == 0 ? one : 0u, w == 1 ? one : 0u, w == 2 ? one : 0u, w == 3 ? one : 0u);
        }
#pragma unroll 1
        for (int b = 0; b < 2; b++) {
          float4* z = reinterpret_cast<float4*>(g_kv[b] + (jj * 4) * KVH + mm * (4 * KVH / 16)) + lane;
#pragma unroll
          for (int i = 0; i < 6; i++) z[i * 32] = make_float4(0.f, 0.f, 0.f, 0.f);
        }
#pragma unroll 1
        for (int i = 0; i < 16; i++) {
          const int b = i >> 2;
          const uint32_t v = (b == 0 ? O_BIT(0) : b == 1 ? X_BIT(0) : H_BIT(0)) + 1;
          uint4* p = b < 2 ? reinterpret_cast<uint4*>(g_obuf + (size_t)(b * S_LEN + mm * 128 + (i & 3) * 32 + (lane >> 3) * 8) * D_MODEL + jj * 128 + (b ? 0 : 64)) + (lane & 7)
                           : g_halo + (size_t)(mm * 8 + jj) * 512 + i * 32 + lane;
          *p = make_uint4(v, v, v, v);
        }
        fence_proxy_async_global();
      }
      __syncwarp();
      uint32_t chkp = 0;
#pragma unroll 1
      for (int lp = hw; lp < 8 * NLAYERS; lp++) {
        const int l = lp >> 3, tk = lp & 7, ph = tk ? 2 - hw : 0;
        const uint32_t par = l & 1;
        int lane; asm volatile("mov.u32 %0, %%laneid;" : "=r"(lane));
        if (tk == 5 || (hw && tk == 0)) {
          const uint32_t bit = ph ? O_BIT(l) : X_BIT(l - 1);
          uint32_t slots = ph ? (uint32_t)(WO_ASLOT(par) >> (ph * 32 - 28)) : 0x8769876u;
          const uint32_t a0 = sbase + (lane & 7) * 126 + lane * 4 + (lane & 1) * 14;
#pragma unroll 1
          for (int c = 0; c < 7; c++, slots >>= 4) {
            const uint32_t cb = bar_chk + 112 - hw * 112 + c * 8;
#pragma unroll 1
            for (int it = 0; it < (1 << 12); it++) {
              mbar_wait_sl(cb, (chkp >> c) & 1);
              chkp ^= 1u << c;
              if (el && c == 0) PROFT(ph == 1 ? 480 + l * 2 : 488 + l * 2 + (ph >> 1));
              uint32_t bad;
              asm volatile("{\n.reg .b32 w<16>;\n"
                           "ld.shared.u32 w0, [%1 + 0];\n"
                           "ld.shared.u32 w1, [%1 + 1024];\n"
                           "ld.shared.u32 w2, [%1 + 2048];\n"
                           "ld.shared.u32 w3, [%1 + 3072];\n"
                           "ld.shared.u32 w4, [%1 + 4096];\n"
                           "ld.shared.u32 w5, [%1 + 5120];\n"
                           "ld.shared.u32 w6, [%1 + 6144];\n"
                           "ld.shared.u32 w7, [%1 + 7168];\n"
                           "ld.shared.u32 w8, [%1 + 8192];\n"
                           "ld.shared.u32 w9, [%1 + 9216];\n"
                           "ld.shared.u32 w10, [%1 + 10240];\n"
                           "ld.shared.u32 w11, [%1 + 11264];\n"
                           "ld.shared.u32 w12, [%1 + 12288];\n"
                           "ld.shared.u32 w13, [%1 + 13312];\n"
                           "ld.shared.u32 w14, [%1 + 14336];\n"
                           "ld.shared.u32 w15, [%1 + 15360];\n"
                           "lop3.b32 w0, w0, w1, %2, 0x7E;\n"
                           "lop3.b32 w2, w2, w3, %2, 0x7E;\n"
                           "lop3.b32 w4, w4, w5, %2, 0x7E;\n"
                           "lop3.b32 w6, w6, w7, %2, 0x7E;\n"
                           "lop3.b32 w8, w8, w9, %2, 0x7E;\n"
                           "lop3.b32 w10, w10, w11, %2, 0x7E;\n"
                           "lop3.b32 w12, w12, w13, %2, 0x7E;\n"
                           "lop3.b32 w14, w14, w15, %2, 0x7E;\n"
                           "lop3.b32 w0, w0, w2, w4, 0xFE;\nlop3.b32 w6, w6, w8, w10, 0xFE;\nlop3.b32 w0, w0, w12, w14, 0xFE;\nlop3.b32 %0, w0, w6, 1, 0xA8;\n}\n"
                           : "=r"(bad) : "r"(a0 + (slots & 15) * SLOT), "r"(bit) : "memory");
              if (__all_sync(0xffffffffu, bad == 0)) break;
              if (el) {
                fence_proxy_async_smem();
                mbar_expect_tx(cb, SLOT);
                tma_load_2d(sbase + (slots & 15) * SLOT, &tm_o, cb, srcb(jj, c) * 128 + (ph >> 1) * 64, mm * 128 + (ph ? 0 : S_LEN));
                RETRY_COUNT();
              }
              __syncwarp();
            }
            if (el) { mbar_arrive_local(bar_full + (c + (ph ? 25 + ph * 8 : 4)) * 8); if (lp == PRL * 8 && c == 0) PROFT(477); }
            __syncwarp();
          }
        } else if (hw && (tk & 5) == 1) {
          {
            const int hp = tk >> 1;
            const uint4* src = reinterpret_cast<const uint4*>(g_colsum[par][jj * 64 + hp * 32 + lane]);
            uint32_t bad;
            int it = 0;
            float c[6];
            do {
              bad = 0;
#pragma unroll
              for (int p = 0; p < 3; p++) {
                const uint4 v = ld_ll(src + ((par && p < 2) ? (hp ? -32 : 512) + p * 32 : p * 512));
                bad |= (v.y ^ ep1) | (v.w ^ ep1);
                c[2 * p] = __uint_as_float(v.x) + __uint_as_float(v.z); c[2 * p + 1] = __uint_as_float(v.y) + __uint_as_float(v.w);
              }
              bad &= 3;
              if (bad) __nanosleep(300);
            } while (bad && ++it < (1 << 16));
#pragma unroll
            for (int p = 0; p < 6; p++) {
              uint32_t h, m, lo;
              split3(c[p], h, m, lo);
              sts128(sbase + OFF_LNB + hp * 4096 + (p >> 1) * 1024 + lane * 32 + (p & 1) * 16, h | (m << 16), h | (lo << 16), h | (m << 16), lo | (m << 16));
            }
            fence_proxy_async_smem();
            __syncwarp();
            if (el) { mbar_arrive_local(hp ? bar_stat2 : bar_stat); if (hp == 0) PROFT(324 + l * 16); }
            __syncwarp();
          }
        } else if (tk == 0) {
          mbar_wait_sl(bar_done + 24, par);
          const uint4* sp = reinterpret_cast<const uint4*>(g_stats + (size_t)(mm * 128) * 8) + lane;
#pragma unroll 1
          for (int hf = 0; hf < 4; hf++) {
            uint4 v[4];
            uint32_t bad;
            int it = 0;
            do {
              bad = 0;
#pragma unroll
              for (int i = 0; i < 4; i++) { v[i] = ld_ll(sp + (hf * 4 + i) * 32); bad |= (v[i].y ^ STAT_TAG(l)) | (v[i].w ^ STAT_TAG(l)); }
              bad &= 3;
              if (bad) __nanosleep(200);
            } while (bad && ++it < (1 << 16));
            __syncwarp();
            float mean = 0.f, m2 = 0.f;
#pragma unroll
            for (int i = 0; i < 4; i++) {
              float a = __uint_as_float(v[i].x) + __uint_as_float(v[i].z);
              a += __shfl_xor_sync(0xffffffffu, a, 1); a += __shfl_xor_sync(0xffffffffu, a, 2);
              a *= 0.125f;
              const float e0 = __uint_as_float(v[i].x) - a, e1 = __uint_as_float(v[i].z) - a;
              float q = fmaf(fmaf(e0, e0, e1 * e1), 128.f, __uint_as_float(v[i].y) + __uint_as_float(v[i].w));
              q += __shfl_xor_sync(0xffffffffu, q, 1); q += __shfl_xor_sync(0xffffffffu, q, 2);
              if ((lane & 3) == i) { mean = a; m2 = q; }
            }
            const uint32_t row = hf * 32 + (lane & 3) * 8 + (lane >> 2);
            uint32_t h, m, lo;
            split3(-0.5f * mean, h, m, lo);
            sts128(sbase + OFF_LNA + row * 16, h | (h << 16), m | (h << 16), lo | (m << 16), m | (lo << 16));
            sts32f(sbase + OFF_ST + row * 4, rsqrtf(m2 * (1.f / 1024.f) + 1e-5f));
          }
          fence_proxy_async_smem();
          __syncwarp();
          if (el) { mbar_arrive_local(bar_stat); PROFT(323 + l * 16); }
          __syncwarp();
#pragma unroll 1
          for (int i = 0; i < 8 - 4 * l; i++) {
            asm volatile("prefetch.global.L2 [%0];" :: "l"(i < 4 ? (l ? prm.wB_o : prm.wA_o) + (size_t)cta * 8192 + i * 2048 + lane * 64
                                                                 : prm.wB_qkv + (size_t)(cta * 8 + (i - 4) * 2 + (lane >> 4)) * 3072 + 2048 + (lane & 15) * 64));
            __nanosleep(PFGAP);
          }
        } else if (lp == 3) {
#pragma unroll 1
          for (int c = 0; c < (NLAYERS > 1 ? 8 : 0); c++) {
            if (!(c & 3)) asm volatile("bar.sync %0, 288;" :: "r"(BAR_WF + (c >> 2)) : "memory");
            if (el) {
              tma_store_2d(&tm_wf, sbase + 11 * SLOT + c * 4096, (c < 4 ? 1024 : -128) + jj * 128 + (c >> 1) * 64, mm * 64 + (c & 1) * 32);
              if ((c & 3) == 3) {
                asm volatile("cp.async.bulk.commit_group;\ncp.async.bulk.wait_group.read 0;" ::: "memory");
                mbar_arrive_local(bar_phi + (c >> 2) * 8);
              } else __nanosleep(WFGAP);
            }
            __syncwarp();
          }
          if (el) { bulk_commit_wait(); signal_release(&g_flags.wfready[jj].v); PROFT(335); }
          __syncwarp();
        } else if (tk == 2 || tk == 4) {
          if (par) continue;
          const int i = tk >> 2;
          mbar_wait_sl(bar_done + (i ? HW1 : (hw ? 19 : HW0)) * 8, 0);
          const uint4* src = g_halo + (size_t)(mm * 8 + jj - 8) * 512 + i * 256 + hw * 128 + lane;
          uint4 v[4];
          int it = 0;
          bool ok;
          do {
#pragma unroll
            for (int j = 0; j < 4; j++) v[j] = mm ? ld_b128(src + j * 32) : make_uint4(H_BIT(l), 0, 0, 0);
            ok = __all_sync(0xffffffffu, (((v[0].x ^ H_BIT(l)) | (v[1].x ^ H_BIT(l)) | (v[2].x ^ H_BIT(l)) | (v[3].x ^ H_BIT(l))) & 1) == 0);
          } while (!ok && ++it < (1 << 16));
          if (lp + hw == 3 && NLAYERS > 1) mbar_wait_sl(bar_phi, 1);
#pragma unroll
          for (int j = 0; j < 4; j++) sts128(sbase + OFF_S + hw * SLOT + j * 512 + lane * 16, v[j].x, v[j].y, v[j].z, v[j].w);
          __syncwarp();
          if (el) { mbar_arrive_local(bar_halo + hw * 8); PROFT(331 + l * 16 + i * 2 + hw); }
          __syncwarp();
        } else if (tk == 6 && hw == 0 && l < NLAYERS - 1) {
          bar_sync<BAR_X1, 288>();
          if (el) {
            PROFT(328 + l * 16);
            mbar_wait_sl(bar_full + XD * 8, par ^ 1);
            tma_store_2d(&tm_o, sbase + 11 * SLOT, jj * 128 + 64, mm * 128 + S_LEN);
            bulk_commit_wait();
            signal_release(&g_flags.xready[l + 1][mm].v);
            PROFT(330 + l * 16);
          }
          __syncwarp();
        }
      }
    }
    cluster_sync();
  } else {
    asm volatile("setmaxnreg.inc.sync.aligned.u32 232;");
    const int wg = warp >> 2;
    const int r0 = warp * 16;
    const uint32_t pK = sbase + OFF_S, pV = sbase + OFF_S + SLOT;
#define PMASKS(on, bit) const uint32_t pm0 = ((on) && t == (g >> 1)), pbit = (bit)
#define PBIT(w) (((w) & ~pm0) | (pbit & pm0))
#define LANE_CONSTS() \
    int lane; asm volatile("mov.u32 %0, %%laneid;" : "=r"(lane)); \
    const int g = lane >> 2, t = lane & 3; \
    const uint32_t srowoff = (r0 + (lane & 15)) * 128, lsw = (lane & 7) << 4, lhi = (lane >> 4) << 4, lsw2 = (lane & 6) << 3; \
    (void)g; (void)t; (void)srowoff; (void)lsw; (void)lhi; (void)lsw2;
    uint32_t stgp = 0, peer;
    asm volatile("mapa.shared::cluster.u32 %0, %1, %2;" : "=r"(peer) : "r"(sbase), "r"(rank ^ 1));
    peer -= sbase;
    const uint32_t dA0 = (((sbase & 0x3FFFF) + wg * 8192) >> 4) | 0x10000u, dB0 = ((sbase & 0x3FFFF) >> 4) | 0x2000000u;
    cluster_wait();
#define DESC(lo, hi) ((uint64_t)(uint32_t)(lo) | ((uint64_t)(hi) << 32))
#define STG_ARRIVE() { __syncwarp(); if (elect_one()) mbar_arrive_local(bar_stg); }
#define STG_WAIT() { mbar_wait(bar_stg, stgp); stgp ^= 1; }
#define PROFS() do {} while (0)
#define REL(addr) { if (elect_one()) { mbar_arrive_local(addr); asm volatile("mbarrier.arrive.shared::cluster.b64 _, [%0];" :: "r"((addr) + peer) : "memory"); } }
#define QSTEP(ACC, DA, SC) { \
      const uint32_t da = (DA), db = dB0 + (ub & 0x18) * (QST >> 7); \
      mbar_wait(ub, par); \
      wgmma_fence(); \
      wgmma4_n192<SC>(ACC, da, db); \
      wgmma_commit(); PROFS(); }
#define QREL() { wgmma_wait<1>(); REL(ub + 376); ub += 8; }
#define RA_CUR (dA0 + (OFF_RA >> 4) + (ub & 0x18) * (SLOT >> 7))
#define PUMP1() { QSTEP(S1, RA_CUR, 1); QREL(); }
#define PUMP0() { PUMP1(); SCHED_FENCE(); }
#define PUMP() if (h == 0) PUMP1()
#define WSTEP() { \
      const uint32_t s4 = (ub - bar_full - 256) >> 1; \
      const uint32_t da = dA0 + (((uint32_t)(WO_ASLOT(par) >> s4) & 15) << 10), db = dB0 + (((uint32_t)(WO_BSLOT >> s4) & 15) << 10); \
      mbar_wait(ub, par); \
      wgmma_fence(); \
      wgmma4_n128<1>(S1, da, db); \
      wgmma_commit(); PROFS(); \
      wgmma_wait<1>(); \
      if (s4) REL(ub + 376); \
      ub += 8; }
#define PUMPS(n) { _Pragma("unroll 1") for (int i_ = 0; i_ < (n); i_++) PUMP1(); }
#define LNSTEP(ACC, hh) { wgmma_fence(); wgmma_n192<1, 0>(ACC, make_desc(sbase + OFF_LNA + wg * 1024, 0, 128) ^ (1ull << 62), make_desc(sbase + OFF_LNB + (hh) * 4096, 0, 128) ^ (1ull << 62)); }
#define WARP_STORE(tm, tile, col, row) { fence_proxy_async_smem(); __syncwarp(); \
      if (elect_one()) { tma_store_2d(tm, (tile) + r0 * 128, col, (row) + r0); asm volatile("cp.async.bulk.commit_group;" ::: "memory"); } __syncwarp(); }
#define TILE_CONSTS(base, on, bit) \
      uint32_t ta[5]; \
      { PMASKS(on, bit); (void)pbit; ta[4] = pm0; } \
      _Pragma("unroll") for (int j = 0; j < 4; j++) ta[j] = (base) + srowoff + ((((uint32_t)j << 5) + lhi) ^ lsw); \
      PINU(ta, 5); SCHED_FENCE(); \
      const uint32_t pm0 = ta[4], pbit = (bit)
#define X_OUT(pc, W) { \
      _Pragma("unroll") for (int j = 0; j < 4; j++) \
        stsm_x4(ta[j] + (pc) * SLOT, \
                PBIT(pack_bf16((W)[j * 8 + 0], (W)[j * 8 + 1])), PBIT(pack_bf16((W)[j * 8 + 2], (W)[j * 8 + 3])), \
                (pack_bf16((W)[j * 8 + 4], (W)[j * 8 + 5])), (pack_bf16((W)[j * 8 + 6], (W)[j * 8 + 7]))); }
#define REST_P1(SKEW) { \
      mbar_wait(bar_stat2, par); \
      LNSTEP(S1, 1); \
      _Pragma("unroll 1") while (ub < bar_full + 256) { \
        if (ub == bar_full + 256 - 8 * (SKEW) && wg == 0) bar_sync<BAR_SKEW, 256>(); \
        QSTEP(S1, RA_CUR, 1); \
        if (ub == bar_full + 248 && wg == 1) bar_arrive<BAR_SKEW, 256>(); \
        QREL(); \
      } \
      mbar_wait(bar_done + (31 - (SKEW)) * 8, par);        \
      wgmma_wait<0>(); \
      ACC_FENCE(S1, 96); \
      REL(bar_done + 31 * 8); \
      PROF(13); }
#define FOLD(tile, rd) { \
          LANE_CONSTS(); \
          float d[32]; \
          ACC_DEF(d, 32); \
          mbar_wait(bar_phi, 0); \
          wgmma_fence(); \
          _Pragma("unroll") for (int i = 0; i < 2; i++) { \
            const uint64_t da = make_desc((tile) + wg * 8192 + i * 64, 16, 1024); \
            const uint64_t db = make_desc(sbase + OFF_PHI + wg * 4096 + i * 2048, 16, 512) ^ (3ull << 62); \
            wgmma_n32<0>(d + i * 16, da, db); wgmma_n32<1>(d + i * 16, da + 2, db + 64); \
          } \
          wgmma_commit(); \
          PUMP0(); \
          ACC_FENCE(d, 32); \
          bar_wg(wg); \
          _Pragma("unroll") for (int i = 0; i < 4; i++) { \
            const float* x = d + (i & 1) * 8 + (i >> 1) * 2; \
            if (rd) sts128((tile) + wg * 8192 + ((warp & 3) * 16 + (i >> 1) * 8 + g) * 128 + (((2 * t + (i & 1)) ^ g) << 4), \
                           pack_bf16(x[0], x[1]), pack_bf16(x[4], x[5]), pack_bf16(x[16], x[17]), pack_bf16(x[20], x[21])); \
            else stsm_x4((tile) + srowoff + ((((uint32_t)i << 5) + lhi) ^ lsw), pack_bf16(d[i * 8], d[i * 8 + 1]), pack_bf16(d[i * 8 + 2], d[i * 8 + 3]), \
                         pack_bf16(d[i * 8 + 4], d[i * 8 + 5]), pack_bf16(d[i * 8 + 6], d[i * 8 + 7])); \
          } \
          }
#define XM_ISSUE() { mbar_wait(bar_xr, par); wgmma_fence(); \
      wgmma_copy(T_, dA0 + (OFF_RA >> 4), make_desc(sbase + OFF_ID, 128, 128) ^ (1ull << 62)); }
#define COPYN(d, s, n) _Pragma("unroll") for (int i_ = 0; i_ < (n); i_++) { uint32_t c_; asm volatile("mov.b32 %0, %1;" : "=r"(c_) : "f"((s)[i_])); (d)[i_] = __uint_as_float(c_); }
#define COPY64(d, s) COPYN(d, s, 64)
#define XM_DONE() { ACC_FENCE(T_, 64); COPY64(S1, T_); ACC_FENCE(S1, 64); \
      __syncwarp(); if (elect_one()) mbar_arrive_local(bar_lx); }
#define LOAD_X() { float T_[64]; ACC_DEF(T_, 64); wgmma_wait<0>(); XM_ISSUE(); wgmma_commit(); wgmma_wait<0>(); XM_DONE(); }

    float S0[96], S1[96];
#define FIRST_STEP(l_) { const int ln_ = (l_), l = ln_; const uint32_t ub = bar_full; (void)l; (void)ub; ACC_DEF(S0, 96); wgmma_fence(); wgmma4_n192<0>(S0, dA0 + (OFF_S >> 4), dB0); wgmma_commit(); PROFS(); }
    mbar_wait(bar_full, 0);
    FIRST_STEP(0);
    LOAD_EPOCH();
#pragma unroll 1
    for (int l = 0;; l++) {
      const uint32_t par = l & 1;
      uint32_t ub = bar_full + 8;
      PROF(1);
      {
        LANE_CONSTS();
        uint32_t ta[4];
#pragma unroll
        for (int j = 0; j < 4; j++) ta[j] = pK + srowoff + ((((uint32_t)j << 5) + lhi) ^ lsw);
        float p0, p1, a0 = 0.f, a1 = 0.f, q0 = 0.f, q1 = 0.f;
#define STATS(j0, j1) _Pragma("unroll") for (int j = (j0); j < (j1); j++) { \
          uint32_t x[4]; \
          ldsm_x4(ta[j & 3] + (j >> 2) * SLOT, x[0], x[1], x[2], x[3]); \
          if (j == 0) { p0 = __shfl_sync(0xffffffffu, bf_lo(x[0]), lane & 28); p1 = __shfl_sync(0xffffffffu, bf_lo(x[1]), lane & 28); } \
          _Pragma("unroll") for (int i = 0; i < 4; i += 2) { \
            const float d0 = bf_lo(x[i]) - p0, d1 = bf_hi(x[i]) - p0, d2 = bf_lo(x[i + 1]) - p1, d3 = bf_hi(x[i + 1]) - p1; \
            a0 += d0 + d1; a1 += d2 + d3; \
            q0 = fmaf(d1, d1, fmaf(d0, d0, q0)); q1 = fmaf(d3, d3, fmaf(d2, d2, q1)); } } \
          asm volatile("" : "+f"(a0), "+f"(a1), "+f"(q0), "+f"(q1), "+f"(p0), "+f"(p1)); SCHED_FENCE()
        if (SB0) { STATS(0, SB0); }
        bar_wg(wg);
        QSTEP(S0, dA0 + ((OFF_S + SLOT) >> 4), 1);
        QREL();
        SCHED_FENCE();
        STATS(SB0, SB1);
        ACC_DEF(S1, 96);
        QSTEP(S1, dA0 + (OFF_S >> 4), 0);
        QREL();
        SCHED_FENCE();
        STATS(SB1, SB2);
        QSTEP(S1, dA0 + ((OFF_S + SLOT) >> 4), 1);
        QREL();
        SCHED_FENCE();
        STATS(SB2, 8);
#pragma unroll
        for (int o = 1; o <= 2; o <<= 1) {
          a0 += __shfl_xor_sync(0xffffffffu, a0, o); a1 += __shfl_xor_sync(0xffffffffu, a1, o);
          q0 += __shfl_xor_sync(0xffffffffu, q0, o); q1 += __shfl_xor_sync(0xffffffffu, q1, o);
        }
        if (t == 1) { a0 = a1; q0 = q1; p0 = p1; }
        if (t < 2) st_b64(g_stats + (size_t)(mm * 128 + r0 + g + t * 8) * 8 + jj, __float_as_uint(fmaf(a0, 1.f / 128.f, p0)),
                          (__float_as_uint(fmaxf(fmaf(a0 * (-1.f / 128.f), a0, q0), 0.f)) & ~3u) | STAT_TAG(l));
        if (l) { asm volatile("cp.async.bulk.wait_group 0;" ::: "memory"); bar_arrive<BAR_X1, 288>(); }
#pragma unroll 1
        for (int i = 0; i < 14; i++) {
          QSTEP(S0, RA_CUR, 1);
          if (i == 0) PROF(2);
          QREL();
        }
      }
      LANE_CONSTS();
      mbar_wait(bar_stat, par);
      LNSTEP(S0, 0);
      wgmma_commit();
      const float rs0 = lds32f(sbase + OFF_ST + (r0 + g) * 4), rs1 = lds32f(sbase + OFF_ST + (r0 + g + 8) * 4);
      PUMP0();
      ACC_FENCE(S0, 96);
      PROF(3);
      if (!par) {
        constexpr uint32_t par = 0;
        uint32_t qa[16];
        uint32_t kf[32], vf[32];
#define DRAIN_A(ACC, hp, PMP) { \
          LANE_CONSTS(); \
          FRAG(kf + 16, ACC + 32, 0, (hp) * 2); \
          PMP; \
          FRAG(vf + 16, ACC + 64, 1, (hp) * 2 + 1); \
          _Pragma("unroll") for (int i_ = 0; i_ < 16; i_++) qa[i_] = pack_bf16(ACC[2 * i_], ACC[2 * i_ + 1]); \
          PINU(qa, 16); }
        DRAIN_A(S0, 0, PUMP0());
        if (l == 0 && NLAYERS > 1) {
#pragma unroll 1
          for (int rd = 1; rd >= 0; rd--) {
            FOLD(sbase + (12 - rd) * SLOT, rd);
            fence_proxy_async_smem();
            asm volatile("bar.arrive %0, 288;" :: "r"(BAR_WF + 1 - rd) : "memory");
          }
        }
        PUMPS(FPUMP);
        if (l == 0 && NLAYERS > 1) mbar_wait(bar_phi, 1);
#pragma unroll 1
        for (int h = 0; h < 2; h++) {
          PROFH(4, 16);
          LANE_CONSTS();
          FRAG_PUT(kf + 16, 10); FRAG_PUT(vf + 16, 11);
          STG_ARRIVE();
          if (h) { PROF(8); LOAD_X(); PROF(9); WSTEP(); PROF(10); } else PUMPS(HPUMP2);
          const bool e = g & 1, hb = (2 * t + (g & 1)) <= g;
          uint32_t sel[3] = {e ? 0x1044u : 0x4410u, hb ? 0x4444u : (e ? 0x3244u : 0x4432u), hb ? (e ? 0x3244u : 0x4432u) : 0x4444u};
          PINU(sel, 3);
          TILE_CONSTS(sbase, true, O_BIT(l));
          const uint32_t selA = sel[0], selL = sel[1], selH = sel[2];
          if (h) PROF(12);
          STG_WAIT();
          if (h) PROF(14);
          if (warp == 0) mbar_wait(bar_halo, h);
          if (h) PROF(15);
          FRAG_GET(kf, 10);
          PROFH(5, 17);
          float s[2][4][4];
#pragma unroll
          for (int ks = 0; ks < 2; ks++)
#pragma unroll
            for (int i = 0; i < 8; i++) {
              const int hh = (i >> 1) & 1, jb = (i & 1) + (~i >> 1 & 2);
              const uint32_t* b = kf + (jb >> 1) * 16 + hh * 8 + ks * 4 + (jb & 1) * 2;
              if (ks) mma_bf16(s[hh][jb], qa[hh * 8 + 4], qa[hh * 8 + 5], qa[hh * 8 + 6], qa[hh * 8 + 7], b[0], b[1]);
              else mma_bf16_z(s[hh][jb], qa[hh * 8], qa[hh * 8 + 1], qa[hh * 8 + 2], qa[hh * 8 + 3], b[0], b[1]);
            }
          PUMP();
          PROFH(6, 18);
          float va[2][2], vb[2][2], mx[2][2];
#pragma unroll
          for (int hh = 0; hh < 2; hh++) {
            va[hh][0] = e ? s[hh][1][1] : s[hh][1][0];
            vb[hh][0] = hb ? (e ? s[hh][2][1] : s[hh][2][0]) : (e ? s[hh][0][1] : s[hh][0][0]);
            va[hh][1] = e ? s[hh][2][3] : s[hh][2][2];
            vb[hh][1] = hb ? (e ? s[hh][3][3] : s[hh][3][2]) : (e ? s[hh][1][3] : s[hh][1][2]);
          }
          if (warp == 0 && mm == 0) {
#pragma unroll
            for (int hh = 0; hh < 2; hh++) { va[hh][0] = -INFINITY; if (!hb) { vb[hh][0] = -INFINITY; vb[hh][1] = -INFINITY; } }
          }
#pragma unroll
          for (int i = 0; i < 4; i++) mx[i >> 1][i & 1] = fmaxf(va[i >> 1][i & 1], vb[i >> 1][i & 1]);
#pragma unroll
          for (int o = 1; o <= 2; o <<= 1)
#pragma unroll
            for (int i = 0; i < 4; i++) mx[i >> 1][i & 1] = fmaxf(mx[i >> 1][i & 1], __shfl_xor_sync(0xffffffffu, mx[i >> 1][i & 1], o));
          const float sc0 = rs0 * (0.17677669529663687f * LOG2E), sc1 = rs1 * (0.17677669529663687f * LOG2E);
#pragma unroll
          for (int i = 0; i < 4; i++) {
            const float sc = (i & 1) ? sc1 : sc0, m = mx[i >> 1][i & 1];
            va[i >> 1][i & 1] = ex2((va[i >> 1][i & 1] - m) * sc); vb[i >> 1][i & 1] = ex2((vb[i >> 1][i & 1] - m) * sc);
            mx[i >> 1][i & 1] = va[i >> 1][i & 1] + vb[i >> 1][i & 1];
          }
          if (h == 0) { PIN(&va[0][0], 4); PIN(&vb[0][0], 4); PIN(&mx[0][0], 4); PUMP1(); }
          if (h) PROF(20);
          if (warp == 0) mbar_wait(bar_halo + 8, h);
          if (h) PROF(21);
          FRAG_GET(vf, 11);
#pragma unroll
          for (int o = 1; o <= 2; o <<= 1)
#pragma unroll
            for (int i = 0; i < 4; i++) mx[i >> 1][i & 1] += __shfl_xor_sync(0xffffffffu, mx[i >> 1][i & 1], o);
          float o[2][4][4];
          uint32_t pa[2][8];
#pragma unroll
          for (int hh = 0; hh < 2; hh++) {
            const float i0 = rcp_fast(mx[hh][0]), i1 = rcp_fast(mx[hh][1]);
            const uint32_t w0 = pack_bf16(va[hh][0] * i0, vb[hh][0] * i0), w1 = pack_bf16(va[hh][1] * i1, vb[hh][1] * i1);
            pa[hh][0] = __byte_perm(w0, 0, selL); pa[hh][2] = __byte_perm(w0, 0, selA); pa[hh][3] = __byte_perm(w1, 0, selL);
            pa[hh][4] = __byte_perm(w0, 0, selH); pa[hh][5] = __byte_perm(w1, 0, selA); pa[hh][7] = __byte_perm(w1, 0, selH);
            pa[hh][1] = pa[hh][0] & pa[hh][4]; pa[hh][6] = pa[hh][3] & pa[hh][7];
          }
          PROFH(7, 19);
#pragma unroll
          for (int i = 0; i < 8; i++) mma_bf16_z(o[i >> 2][i & 3], pa[i >> 2][4], pa[i >> 2][5], pa[i >> 2][6], pa[i >> 2][7], vf[16 + 2 * i], vf[17 + 2 * i]);
#pragma unroll
          for (int i = 0; i < 8; i++) mma_bf16(o[i >> 2][i & 3], pa[i >> 2][0], pa[i >> 2][1], pa[i >> 2][2], pa[i >> 2][3], vf[2 * i], vf[2 * i + 1]);
          if (h == 0) PUMP1() else mbar_wait(bar_done + 30 * 8, par);
          if (NLAYERS > 1) mbar_wait(bar_phi + 8, 0);
          if (h) PROF(22);
#pragma unroll
          for (int i = 0; i < 4; i++) {
            const int hh = i >> 1, dp = i & 1;
            stsm_x4(ta[i] + (h ? 3 : 12) * SLOT,
                    PBIT(pack_bf16(o[hh][dp * 2][0], o[hh][dp * 2][1])), PBIT(pack_bf16(o[hh][dp * 2][2], o[hh][dp * 2][3])),
                    pack_bf16(o[hh][dp * 2 + 1][0], o[hh][dp * 2 + 1][1]), pack_bf16(o[hh][dp * 2 + 1][2], o[hh][dp * 2 + 1][3]));
          }
          WARP_STORE(&tm_os, sbase + (h ? 3 : 12) * SLOT, jj * 128 + h * 64, mm * 128);
          PROFH(11, 23);
          if (h) break;
          REST_P1(ASKEW);
          asm volatile("cp.async.bulk.wait_group.read 0;" ::: "memory");
          DRAIN_A(S1, 1, {});
        }
      } else {
        constexpr uint32_t par = 1;
        float st[32];
        const float c0 = rs0 * LOG2E, c1 = rs1 * LOG2E;
        { V_ADDR(pV); STAGE_V(S0 + 64); }
        if (warp < 2) sts128(sbase + OFF_ONES + warp * 512 + lane * 16, 0x3F803F80u, 0x3F803F80u, 0x3F803F80u, 0x3F803F80u);
        scale32(st, S0, c0, c1);
        PIN(st, 32);
#define PHI_PIECE(c) { \
          e_[2 * (c)] = ex2(st[2 * (c)]); e_[2 * (c) + 1] = ex2(st[2 * (c) + 1]); \
          _Pragma("unroll") for (int k_ = 4 * (c); k_ < 4 * (c) + 4; k_++) m_[(c) >> 1] = (k_ & 7) ? fmaf(st[k_], st[k_], m_[(c) >> 1]) : st[k_] * st[k_]; \
          asm volatile("" : "+f"(e_[2 * (c)]), "+f"(e_[2 * (c) + 1]), "+f"(m_[(c) >> 1])); SCHED_FENCE(); }
#define PHI_FIN() { \
          big = __any_sync(0xffffffffu, !(fmaxf(fmaxf(m_[0], m_[1]), fmaxf(m_[2], m_[3])) < BIGLIM)); \
          if (__builtin_expect(big, 0)) { COPYN(e_, st, 16); } \
          _Pragma("unroll") for (int k_ = 0; k_ < 16; k_++) st[k_] = e_[k_]; \
          PIN(st, 16); }
#define KV_MMA(vs, IL) { \
          const uint32_t dp = dA0 + 12 * 1024 - wg * 2560, dv = dA0 + (vs) * 1024 + ((OFF_ONES - (vs) * SLOT - 16) << 12) - wg * (512 << 16); \
          STG_WAIT(); \
          wgmma_fence(); \
          _Pragma("unroll") for (int ks = 0; ks < 8; ks++) { \
            const uint64_t a = DESC(dp + ks * 128, 0x40000040), b = DESC(dv + ks * (64 - (64 << 16)), 0x80000020); \
            if ((IL) && ks) wgmma_fence(); \
            if (ks == 0) wgmma_n40<0, 1>(kv, a, b); else wgmma_n40<1, 1>(kv, a, b); \
            if (ks == 7) wgmma_commit(); \
            if (IL) PHI_PIECE(ks); } }
#define KV_RED1(i) if (h) red_v4(g_kv[l >> 1] + (jj * 4) * KVH + warp * 768 + lane * 4 + (i) * 128, S0[32 + (i) * 3], S0[33 + (i) * 3], S0[34 + (i) * 3], 1.f)
#define KV_REDS(n) { _Pragma("unroll") for (int i_ = 0; i_ < 6; i_++) if (((RPACE >> (4 * i_)) & 15) == (n)) KV_RED1(i_); }
#define KV_SEND(kp) { \
          float sd[9]; \
          kv[17] = kv[18]; \
          _Pragma("unroll") for (int i = 0; i < 9; i++) { (kp)[i] = rank ? kv[9 + i] : kv[i]; sd[i] = rank ? kv[i] : kv[9 + i]; } \
          const uint32_t ra = sbase + peer + (warp * 32 + lane) * 4, rb = bar_kx + peer; \
          if (elect_one()) mbar_expect_tx(bar_kx, 1152); \
          _Pragma("unroll") for (int i = 0; i < 2; i++) \
            asm volatile("st.async.weak.shared::cluster.mbarrier::complete_tx::bytes.v4.f32 [%0], {%1, %2, %3, %4}, [%5];" \
                         :: "r"(ra + (warp * 32 + lane) * 12 + OFF_PHI + i * 4096), "f"(sd[4 * i]), "f"(sd[4 * i + 1]), "f"(sd[4 * i + 2]), "f"(sd[4 * i + 3]), "r"(rb) : "memory"); \
          asm volatile("st.async.weak.shared::cluster.mbarrier::complete_tx::bytes.f32 [%0], %1, [%2];" :: "r"(ra + OFF_LNB), "f"(sd[8]), "r"(rb) : "memory"); }
#define KV_RECV(kp, hp) { \
          float r_[9]; \
          float* kvg = g_kv[l >> 1] + (jj * 4 + (hp) * 2) * KVH + warp * 768 + rank * 384 + lane * 4; \
          mbar_wait(bar_kx, l >> 1); \
          _Pragma("unroll") for (int i = 0; i < 2; i++) \
            asm volatile("ld.shared.v4.f32 {%0, %1, %2, %3}, [%4];" : "=f"(r_[4 * i]), "=f"(r_[4 * i + 1]), "=f"(r_[4 * i + 2]), "=f"(r_[4 * i + 3]) \
                         : "r"(sbase + OFF_PHI + i * 4096 + (warp * 32 + lane) * 16) : "memory"); \
          r_[8] = lds32f(sbase + OFF_LNB + (warp * 32 + lane) * 4); \
          _Pragma("unroll") for (int i = 0; i < 3; i++) red_v4(kvg + i * 128, (kp)[3 * i] + r_[3 * i], (kp)[3 * i + 1] + r_[3 * i + 1], (kp)[3 * i + 2] + r_[3 * i + 2], 2.f); }
#define KV_LOAD(hp) { \
          const uint4* kvg = reinterpret_cast<const uint4*>(g_kv[l >> 1] + (jj * 4 + (hp) * 2) * KVH) + warp * 192 + lane; \
          _Pragma("unroll") for (int i = 0; i < 6; i++) v[i] = ld_b128(kvg + i * 32); }
#define KVV(i) __uint_as_float((i) % 3 == 0 ? v[(i) / 3].x : ((i) % 3 == 1 ? v[(i) / 3].y : v[(i) / 3].z))
#define KV_TILE(hp) { \
          _Pragma("unroll 1") for (int it = 0; it < (1 << 16); it++) { \
            if (__all_sync(0xffffffffu, (v[0].w & v[1].w & v[2].w & v[3].w & v[4].w & v[5].w) == 0x41800000u)) break; \
            RETRY_COUNT(); \
            KV_LOAD(hp); \
          } \
          if (hp) PROF(26); else PROF(25); \
          const uint32_t e = lane & 7, jt = ((lane >> 1) & 4) + (e >> 1); \
          const uint32_t row = ((((warp >> 1) ^ wg) & 1) << 5) + ((jt & 1) << 4) + ((warp & 1) << 3) + (jt & 6) + (e & 1); \
          const uint32_t kd = pV + wg * 8192 + row * 128, ksw = (row & 7) << 4; \
          _Pragma("unroll") for (int i = 0; i < 2; i++) \
            stsm_x4(kd + ((i * 32 + lhi) ^ ksw), pack_bf16(KVV(i * 8), KVV(i * 8 + 1)), pack_bf16(KVV(i * 8 + 2), KVV(i * 8 + 3)), \
                    pack_bf16(KVV(i * 8 + 4), KVV(i * 8 + 5)), pack_bf16(KVV(i * 8 + 6), KVV(i * 8 + 7))); \
          stsm_x4(kd + ((64u + lhi) ^ ksw), pack_bf16(KVV(16), 1.f), pack_bf16(KVV(17), 1.f), 0u, 0u); }
#pragma unroll 1
        for (int h = 0; h < 2; h++) {
          PROFH(4, 6);
          PUMP0();
          LANE_CONSTS();
          const uint32_t dsw = (uint32_t)(g ^ (2 * t)) << 4, dst = ((t & 2) ? pK : sbase + 12 * SLOT) + (r0 + g) * 128;
          float e[16], f[16];
          KV_REDS(1);
          float sa = exps16_<0>(e, st);
          exps16_fix<0>(e, st, sa);
          asm volatile("" : "+f"(sa)); PIN(e, 16); PUMP0();
          if (h) STG_WAIT();
          KV_REDS(2);
          store16(e, sa, dst, dsw, 4);
          float sb = exps16_<1>(f, st);
          exps16_fix<1>(f, st, sb);
          asm volatile("" : "+f"(sb)); PIN(f, 16); PUMP0();
          KV_REDS(3);
          store16(f, sb, dst, dsw, 0);
          float sc = exps16_<0>(e, st + 2);
          exps16_fix<0>(e, st + 2, sc);
          asm volatile("" : "+f"(sc)); PIN(e, 16); PUMP0();
          KV_REDS(4);
          store16(e, sc, dst + 1024, dsw, 4);
          float sd = exps16_<1>(f, st + 2);
          exps16_fix<1>(f, st + 2, sd);
          asm volatile("" : "+f"(sd)); PIN(f, 16); PUMP0();
          store16(f, sd, dst + 1024, dsw, 0);
          PROFH(5, 7);
          if (h) break;
          {
            float kv[20];
            ACC_DEF(kv, 20);
            fence_proxy_async_smem();
            STG_ARRIVE();
            float e_[16], m_[4];
            KV_MMA(11, 0);
            PUMP0();
            ACC_FENCE(kv, 20);
            STG_ARRIVE();
            scale32(st, S0 + 32, c0, c1);
            PIN(st, 32);
            {
              kv[17] = kv[18];
              COPYN(S0 + 32, kv, 18);
              const int h = 1;
              KV_REDS(0);
            }
          }
        }
        bool big;
        uint4 v[6];
        {
          float kv[20];
          { LANE_CONSTS(); KV_LOAD(0); }
          mbar_wait(bar_stat2, par);
          LNSTEP(S1, 1);
          ub = bar_full + 240;
          PUMP1();
          if (wg == 0) bar_sync<BAR_SKEW, 256>();
          QSTEP(S1, RA_CUR, 1);
          if (wg == 1) bar_arrive<BAR_SKEW, 256>();
          QREL();
          { LANE_CONSTS(); KV_TILE(0); }
          LANE_CONSTS();
          V_ADDR(sbase + 3 * SLOT);
          PINU(va_, 2);
          mbar_wait(bar_done + 30 * 8, par);
          wgmma_wait<0>();
          ACC_FENCE(S1, 96);
          PROF(13);
          STAGE_V(S1 + 64);
          fence_proxy_async_smem();
          STG_ARRIVE();
          REL(bar_done + 31 * 8);
          scale32(st, S1, c0, c1);
          PIN(st, 32);
          PROF(16);
          ACC_DEF(kv, 20);
          float e_[16], m_[4];
          KV_MMA(3, 1);
          SCHED_FENCE();
          PROF(14);
          PHI_FIN();
          SCHED_FENCE();
          PROF(15);
          wgmma_wait<0>();
          ACC_FENCE(kv, 20);
          PROF(12);
          { float kp[9]; KV_SEND(kp); _Pragma("unroll") for (int i = 0; i < 3; i++) v[i] = make_uint4(__float_as_uint(kp[3 * i]), __float_as_uint(kp[3 * i + 1]), __float_as_uint(kp[3 * i + 2]), 0u); }
          PROF(17);
        }
#pragma unroll 1
        for (int h = 0; h < 2; h++) {
          const uint32_t pO = sbase + (h ? 3 : 8) * SLOT;
          LANE_CONSTS();
          uint32_t fq[32];
          PROFH(18, 32);
          SCHED_FENCE();
          phiq_b<1>(fq, st, big); PINU(fq, 16); PIN(st + 16, 16);
          SCHED_FENCE();
          PROFH(8, 9);
          if (h) {
            asm volatile("cp.async.bulk.wait_group.read 0;" ::: "memory");
            mbar_wait(bar_lx, par);
            PROF(30);
            KV_TILE(1);
            fence_proxy_async_smem();
            STG_ARRIVE();
          }
          SCHED_FENCE();
          if (h == 0) {
            float kp[9];
#pragma unroll
            for (int i = 0; i < 9; i++) kp[i] = KVV(i);
            KV_RECV(kp, 1);
            SCHED_FENCE();
          }
          phiq_b<0>(fq + 16, st + 16, big); PINU(fq + 16, 16);
          PROFH(10, 21);
          if (h) STG_WAIT();
          wgmma_wait<0>();
          ACC_FENCE(S1, 64);
          PROFH(19, 33);
          float o[4][20];
#define O_MMA(hh) { \
            const uint64_t db = make_desc(pV + (hh) * 8192, 16, 1024); \
            ACC_DEF(o[(hh) * 2], 20); ACC_DEF(o[(hh) * 2 + 1], 20); \
            wgmma_fence(); \
            wgmma_n40_rs<0>(o[(hh) * 2], fq + (hh) * 16, db + 256); wgmma_n40_rs<0>(o[(hh) * 2 + 1], fq + (hh) * 16 + 8, db); \
            wgmma_n40_rs<1>(o[(hh) * 2], fq + (hh) * 16 + 4, db + 384); wgmma_n40_rs<1>(o[(hh) * 2 + 1], fq + (hh) * 16 + 12, db + 128); \
            wgmma_commit(); }
          O_MMA(0);
          SCHED_FENCE();
          PMASKS(true, O_BIT(l));
#pragma unroll
          for (int hh = 0; hh < 2; hh++) {
            wgmma_wait<0>();
            ACC_FENCE(o[hh * 2], 20); ACC_FENCE(o[hh * 2 + 1], 20);
            if (!hh) { O_MMA(1); SCHED_FENCE(); }
            if (hh) PROFH(22, 24);
            const float* x = o[hh * 2];
            const float* y = o[hh * 2 + 1];
            const float sx0 = x[17] * 0x1p-40f, sy0 = y[17] * 0x1p-40f, sx1 = x[19] * 0x1p-40f, sy1 = y[19] * 0x1p-40f;
            const float i0 = rcp_fast(fmaf(fmaf(x[17], 1e-6f, x[16]), sy0, y[16] * sx0)), i1 = rcp_fast(fmaf(fmaf(x[19], 1e-6f, x[18]), sy1, y[18] * sx1));
            const float ax0 = sy0 * i0, ay0 = sx0 * i0, ax1 = sy1 * i1, ay1 = sx1 * i1;
#pragma unroll
            for (int dp = 0; dp < 2; dp++)
              stsm_x4(pO + srowoff + ((hh * 64 + dp * 32 + lhi) ^ lsw),
                      PBIT(pack_bf16(fmaf(x[dp * 8], ax0, y[dp * 8] * ay0), fmaf(x[dp * 8 + 1], ax0, y[dp * 8 + 1] * ay0))),
                      PBIT(pack_bf16(fmaf(x[dp * 8 + 2], ax1, y[dp * 8 + 2] * ay1), fmaf(x[dp * 8 + 3], ax1, y[dp * 8 + 3] * ay1))),
                      (pack_bf16(fmaf(x[dp * 8 + 4], ax0, y[dp * 8 + 4] * ay0), fmaf(x[dp * 8 + 5], ax0, y[dp * 8 + 5] * ay0))),
                      (pack_bf16(fmaf(x[dp * 8 + 6], ax1, y[dp * 8 + 6] * ay1), fmaf(x[dp * 8 + 7], ax1, y[dp * 8 + 7] * ay1))));
          }
          WARP_STORE(&tm_os, pO, jj * 128 + h * 64, mm * 128);
          PROFH(20, 34);
          if (h) break;
          float T_[64];
          scale32(st, S1 + 32, c0, c1);
          PIN(st, 32);
          ACC_DEF(T_, 64);
          XM_ISSUE(); wgmma_commit();
          SCHED_FENCE();
          big = any_big(st);
          SCHED_FENCE();
          PROF(27);
          wgmma_wait<0>(); XM_DONE();
          PROF(28);
          bar_wg(wg);
          WSTEP();
          SCHED_FENCE();
          PROF(29);
          KV_LOAD(1);
          phiq_a(st, big); PIN(st, 16);
          PROF(31);
        }
      }
      __syncwarp();
      if (elect_one()) mbar_arrive_local(bar_epi);
      bar_wg(wg);
#pragma unroll 1
      while (ub < bar_full + 384) {
        WSTEP();
        if (ub == bar_full + 8 * 41) { asm volatile("cp.async.bulk.wait_group.read 0;" ::: "memory"); PROF(35); }
        if (ub == bar_full + 8 * 42) PROF(36);
      }
      {
        float Wb[32];
        LANE_CONSTS();
        TILE_CONSTS(pK, l < NLAYERS - 1, X_BIT(l));
        if (l < NLAYERS - 1) mbar_wait(bar_full, par ^ 1);
        wgmma_wait<0>();
        ACC_FENCE(S1, 64);
        COPYN(Wb, S1 + 32, 32);
        PROF(37);
        X_OUT(0, S1);
        WARP_STORE(l < NLAYERS - 1 ? &tm_os : &tm_xo, pK, jj * 128, mm * 128 + (l < NLAYERS - 1 ? S_LEN : 0));
        if (l == NLAYERS - 1) { PMASKS(false, 0); X_OUT(1, Wb); break; }
        PROF(38);
        bar_wg(wg);
        FIRST_STEP(l + 1);
        REL(bar_done + 47 * 8);
        PROF(39);
        { PMASKS(false, 0); X_OUT(1, Wb); }
        fence_proxy_async_smem();
      }
    }
    WARP_STORE(&tm_xo, pV, jj * 128 + 64, mm * 128);
    asm volatile("cp.async.bulk.wait_group.read 0;" ::: "memory");
    cluster_sync();
  }
}

typedef CUresult (*PFN_encode)(CUtensorMap*, CUtensorMapDataType, cuuint32_t, void*, const cuuint64_t*, const cuuint64_t*,
                               const cuuint32_t*, const cuuint32_t*, CUtensorMapInterleave, CUtensorMapSwizzle,
                               CUtensorMapL2promotion, CUtensorMapFloatOOBfill);

CUtensorMap make_map(PFN_encode enc, const void* ptr, uint64_t inner, uint64_t outer, uint32_t box_inner, uint32_t box_outer,
                     CUtensorMapSwizzle swz = CU_TENSOR_MAP_SWIZZLE_128B, int promo = CU_TENSOR_MAP_L2_PROMOTION_L2_256B) {
  CUtensorMap m;
  cuuint64_t dims[2] = {inner, outer};
  cuuint64_t strides[1] = {inner * 2};
  cuuint32_t box[2] = {box_inner, box_outer};
  cuuint32_t es[2] = {1, 1};
  enc(&m, CU_TENSOR_MAP_DATA_TYPE_BFLOAT16, 2, const_cast<void*>(ptr), dims, strides, box, es, CU_TENSOR_MAP_INTERLEAVE_NONE,
      swz, (CUtensorMapL2promotion)promo, CU_TENSOR_MAP_FLOAT_OOB_FILL_NONE);
  return m;
}

}

extern "C" void kernel_launch(void* const* d_in, const int* in_sizes, int n_in, void* d_out, int out_size) {
  (void)in_sizes; (void)n_in; (void)out_size;
  static PFN_encode enc = nullptr;
  if (!enc) {
    void* fn = nullptr;
    cudaDriverEntryPointQueryResult qr;
    cudaGetDriverEntryPoint("cuTensorMapEncodeTiled", &fn, cudaEnableDefault, &qr);
    enc = (PFN_encode)fn;
    cudaFuncSetAttribute(mega_kernel, cudaFuncAttributeMaxDynamicSharedMemorySize, SMEM_BYTES);
  }
  Params prm;
  prm.x0 = (const __nv_bfloat16*)d_in[0];
  prm.wA_qkv = (const __nv_bfloat16*)d_in[1];
  prm.wA_o = (const __nv_bfloat16*)d_in[2];
  prm.wB_qkv = (const __nv_bfloat16*)d_in[4];
  prm.wB_phi = (const __nv_bfloat16*)d_in[5];
  prm.wB_o = (const __nv_bfloat16*)d_in[6];
  prm.out = (__nv_bfloat16*)d_out;
  void *obuf = nullptr, *wf = nullptr;
  cudaGetSymbolAddress(&obuf, g_obuf);
  cudaGetSymbolAddress(&wf, g_wfold);
  CUtensorMap tm_x0 = make_map(enc, d_in[0], D_MODEL, S_LEN, 64, 128, CU_TENSOR_MAP_SWIZZLE_128B, XPROMO);
  CUtensorMap tm_xo = make_map(enc, d_out, D_MODEL, S_LEN, 64, 16);
  CUtensorMap tm_os = make_map(enc, obuf, D_MODEL, 2 * S_LEN, 64, 16);
  CUtensorMap tm_o = make_map(enc, obuf, D_MODEL, 2 * S_LEN, 64, 128, CU_TENSOR_MAP_SWIZZLE_128B, OPROMO);
  CUtensorMap tm_wf = make_map(enc, wf, 2048, D_MODEL, 64, 32);
  CUtensorMap tm_wqA = make_map(enc, d_in[1], 3 * D_MODEL, D_MODEL, 64, 32, CU_TENSOR_MAP_SWIZZLE_128B, WPROMO);
  CUtensorMap tm_wqB = make_map(enc, prm.wB_qkv, 3 * D_MODEL, D_MODEL, 64, 32);
  CUtensorMap tm_woA = make_map(enc, prm.wA_o, D_MODEL, D_MODEL, 64, 64);
  CUtensorMap tm_woB = make_map(enc, prm.wB_o, D_MODEL, D_MODEL, 64, 64);
  CUtensorMap tm_phi = make_map(enc, prm.wB_phi, 32, 1024, 32, 128, CU_TENSOR_MAP_SWIZZLE_64B);
  mega_kernel<<<NMAIN + NAUX, 384, SMEM_BYTES>>>(tm_x0, tm_xo, tm_os, tm_o, tm_wf, tm_wqA, tm_wqB, tm_woA, tm_woB, tm_phi, prm);
}
```

```cpp
#include <cuda_runtime.h>
#include <cuda.h>
#include <cuda_bf16.h>
#include <stdint.h>

#define NLAYERS 4

#define HPUMP2 1
#define ASKEW 2
#define FPUMP 3
#define PFGAP 100
#define POLLGAP 120
#define HW1 29
#define XPACE 0x06050401000000ull
#define XP0 4
#define HW0 18
#define XD 4
#define WFGAP 50
#define EARLY 2
#define BIGLIM 3600.f
#define SUMLO 0x1p-100f
#define SUMHI 0x1p100f
#define XPROMO 2
#define OPROMO 3
#define STAG2 300
#define WPROMO 3
#define SB0 2
#define SB1 4
#define SB2 6
#define PROWS 3
#define SPD0 0
#define SPD1 0
#define SPD2 300
#define FRB 0x3535353535ull
#define NOB 0xFFFFFF00u
#define NO1 ~0u
#define NOX ~0u
#define FD0 0
#define FD1 3
#define RPACE 0x221100
namespace {

constexpr int S_LEN = 2048, D_MODEL = 1024;
constexpr int NAUX = 4, NMAIN = 128;
constexpr int SLOT = 16384;
constexpr int QST = 24576;
constexpr int OFF_RA = 6 * SLOT, OFF_S = 10 * SLOT;
constexpr int OFF_HALO = 13 * SLOT, OFF_LNB = OFF_HALO  , OFF_ONES = OFF_HALO + 3072;
constexpr int OFF_ST = OFF_HALO + 7168  , OFF_ID = OFF_HALO + 7680, OFF_PHI = OFF_HALO + 8192;
constexpr int OFF_BAR = 14 * SLOT;
constexpr int OFF_LNA = OFF_BAR + 1024;
constexpr int SMEM_BYTES = OFF_LNA + 2048;
#define WO_ASLOT(par) ((par) ? 0x9876CAB39876CA98ull : 0x98C76BA398C7698Cull)
constexpr unsigned long long WO_BSLOT = 0x5432105421054210ull;
__device__ __forceinline__ int srcb(int j, int i) { return (i + (i >= j)) & 7; }
__device__ __forceinline__ int kslice(int j, int i) { return i < 2 ? 2 * j + i : (i < 9 ? 2 * srcb(j, i - 2) : 2 * srcb(j, i - 9) + 1); }
__device__ __forceinline__ int wslice(int j, int s) { return 2 * ((s & 7) ? srcb(j, (s & 7) - 1) : j) + (s >> 3); }
constexpr int KVH = 6 * 128 * 4;

struct __align__(128) Flag { unsigned v; unsigned pad[31]; };
struct Flags {
  Flag xready[4][16];
  Flag wfready[8];
  Flag done;
  Flag epoch;
};

__device__ Flags g_flags;
__device__ __nv_bfloat16 g_obuf[2 * S_LEN * D_MODEL];
#define O_BIT(l) ((epoch * NLAYERS + (l) + 1) & 1u)
#define X_BIT(l) ((epoch * (NLAYERS - 1) + (l) + 1) & 1u)
__device__ __nv_bfloat16 g_wfold[D_MODEL * 2048];
__device__ uint4 g_halo[16 * 8 * 512];
__device__ __align__(128) float g_kv[2][32 * KVH];
__device__ __align__(128) uint2 g_colsum[2][1536][2];
__device__ __align__(128) uint2 g_stats[S_LEN * 8];
#define H_BIT(l) (NLAYERS > 2 ? (uint32_t)((l) == 0) : (ep1 & 1))
#define STAT_TAG(l) ((ep1 * NLAYERS + (l) + 1) & 3u)

#define RETRY_COUNT()
#define PRL 0
#define PRU 0
#define PROFL 1
#define PROFW 0
#define PROFT(i) do {} while (0)
#define PROF(i) do {} while (0)
#define PROFH(i, j) do {} while (0)

__device__ __forceinline__ uint32_t smem_u32(const void* p) { return (uint32_t)__cvta_generic_to_shared(p); }
__device__ __forceinline__ bool elect_one() {
  uint32_t p;
  asm volatile("{\n.reg .pred p;\nelect.sync _|p, 0xffffffff;\nselp.u32 %0, 1, 0, p;\n}\n" : "=r"(p));
  return p != 0;
}
__device__ __forceinline__ void mbar_init(uint32_t bar, uint32_t cnt) {
  asm volatile("mbarrier.init.shared::cta.b64 [%0], %1;" :: "r"(bar), "r"(cnt));
}
__device__ __forceinline__ void mbar_expect_tx(uint32_t bar, uint32_t bytes) {
  asm volatile("mbarrier.arrive.expect_tx.shared::cta.b64 _, [%0], %1;" :: "r"(bar), "r"(bytes) : "memory");
}
#define mbar_wait(bar, parity) \
  asm volatile("{\n.reg .pred p, q;\nW_%=:\nmbarrier.try_wait.parity.shared::cta.b64 p, [%1], %2;\nadd.s32 %0, %0, -1;\n" \
               "setp.gt.and.s32 q, %0, 0, !p;\n@q bra.uni W_%=;\n}\n" : "+r"(budget) : "r"((uint32_t)(bar)), "r"((uint32_t)(parity)) : "memory")
#define mbar_wait_sl(bar, parity) \
  asm volatile("{\n.reg .pred p, q;\nW_%=:\nmbarrier.try_wait.parity.shared::cta.b64 p, [%1], %2, 20000;\nadd.s32 %0, %0, -64;\n" \
               "setp.gt.and.s32 q, %0, 0, !p;\n@q bra.uni W_%=;\n}\n" : "+r"(budget) : "r"((uint32_t)(bar)), "r"((uint32_t)(parity)) : "memory")
__device__ __forceinline__ void mbar_arrive_local(uint32_t bar) {
  asm volatile("mbarrier.arrive.shared::cta.b64 _, [%0];" :: "r"(bar) : "memory");
}
__device__ __forceinline__ void tma_load_2d(uint32_t dst, const CUtensorMap* tm, uint32_t bar, int c0, int c1) {
  asm volatile("cp.async.bulk.tensor.2d.shared::cluster.global.mbarrier::complete_tx::bytes [%0], [%1, {%3, %4}], [%2];"
               :: "r"(dst), "l"(tm), "r"(bar), "r"(c0), "r"(c1) : "memory");
}
__device__ __forceinline__ void tma_load_2d_mc(uint32_t dst, const CUtensorMap* tm, uint32_t bar, int c0, int c1) {
  asm volatile("cp.async.bulk.tensor.2d.shared::cluster.global.mbarrier::complete_tx::bytes.multicast::cluster [%0], [%1, {%3, %4}], [%2], %5;"
               :: "r"(dst), "l"(tm), "r"(bar), "r"(c0), "r"(c1), "h"((uint16_t)3) : "memory");
}
__device__ __forceinline__ void tma_store_2d(const CUtensorMap* tm, uint32_t src, int c0, int c1) {
  asm volatile("cp.async.bulk.tensor.2d.global.shared::cta.bulk_group [%0, {%2, %3}], [%1];"
               :: "l"(tm), "r"(src), "r"(c0), "r"(c1) : "memory");
}
__device__ __forceinline__ void bulk_commit_wait() {
  asm volatile("cp.async.bulk.commit_group;\ncp.async.bulk.wait_group 0;" ::: "memory");
}
__device__ __forceinline__ void prefetch_tmap(const CUtensorMap* tm) {
  asm volatile("prefetch.tensormap [%0];" :: "l"(tm) : "memory");
}
__device__ __forceinline__ void fence_proxy_async_global() { asm volatile("fence.proxy.async.global;" ::: "memory"); }
__device__ __forceinline__ void fence_proxy_async_smem() { asm volatile("fence.proxy.async.shared::cta;" ::: "memory"); }
__device__ __forceinline__ unsigned ld_relaxed(const unsigned* p) {
  unsigned v;
  asm volatile("ld.relaxed.gpu.global.u32 %0, [%1];" : "=r"(v) : "l"(p) : "memory");
  return v;
}
__device__ __forceinline__ void fence_acquire() { asm volatile("fence.acquire.gpu;" ::: "memory"); }
__device__ __forceinline__ void wait_flag(const unsigned* p, unsigned target) {
  int it = 0;
  while ((int)(ld_relaxed(p) - target) < 0 && ++it < (1 << 20)) {}
  fence_acquire();
}
__device__ __forceinline__ void signal_release(unsigned* p) {
  asm volatile("red.release.gpu.global.add.u32 [%0], 1;" :: "l"(p) : "memory");
}
template <int ID, int N> __device__ __forceinline__ void bar_arrive() { asm volatile("bar.arrive %0, %1;" :: "n"(ID), "n"(N) : "memory"); }
template <int ID, int N> __device__ __forceinline__ void bar_sync() { asm volatile("bar.sync %0, %1;" :: "n"(ID), "n"(N) : "memory"); }
__device__ __forceinline__ void bar_wg(int wg) { asm volatile("bar.sync %0, 128;" :: "r"(2 + wg) : "memory"); }
__device__ __forceinline__ void cluster_sync() {
  asm volatile("barrier.cluster.arrive.relaxed.aligned;\nbarrier.cluster.wait.aligned;" ::: "memory");
}
__device__ __forceinline__ void cluster_wait() { asm volatile("barrier.cluster.wait.acquire.aligned;" ::: "memory"); }
enum { BAR_X1 = 7, BAR_WF = 8  , BAR_SKEW = 10 };

__device__ __forceinline__ void wgmma_fence() { asm volatile("wgmma.fence.sync.aligned;" ::: "memory"); }
__device__ __forceinline__ void wgmma_commit() { asm volatile("wgmma.commit_group.sync.aligned;" ::: "memory"); }
template <int N> __device__ __forceinline__ void wgmma_wait() { asm volatile("wgmma.wait_group.sync.aligned %0;" :: "n"(N) : "memory"); }

template <int scale_d, int tnsp_b = 1> __device__ __forceinline__ void wgmma_n192(float* d, uint64_t descA, uint64_t descB) {
  asm volatile("{\n.reg .pred p;\nsetp.ne.b32 p, %98, 0;\n"
               "wgmma.mma_async.sync.aligned.m64n192k16.f32.bf16.bf16 {%0,%1,%2,%3,%4,%5,%6,%7,%8,%9,%10,%11,%12,%13,%14,%15,%16,%17,%18,%19,%20,%21,%22,%23,%24,%25,%26,%27,%28,%29,%30,%31,%32,%33,%34,%35,%36,%37,%38,%39,%40,%41,%42,%43,%44,%45,%46,%47,%48,%49,%50,%51,%52,%53,%54,%55,%56,%57,%58,%59,%60,%61,%62,%63,%64,%65,%66,%67,%68,%69,%70,%71,%72,%73,%74,%75,%76,%77,%78,%79,%80,%81,%82,%83,%84,%85,%86,%87,%88,%89,%90,%91,%92,%93,%94,%95}, %96, %97, p, 1, 1, 0, %99;\n}\n"
               : "+f"(d[0]), "+f"(d[1]), "+f"(d[2]), "+f"(d[3]), "+f"(d[4]), "+f"(d[5]), "+f"(d[6]), "+f"(d[7]), "+f"(d[8]), "+f"(d[9]), "+f"(d[10]), "+f"(d[11]), "+f"(d[12]), "+f"(d[13]), "+f"(d[14]), "+f"(d[15]), "+f"(d[16]), "+f"(d[17]), "+f"(d[18]), "+f"(d[19]), "+f"(d[20]), "+f"(d[21]), "+f"(d[22]), "+f"(d[23]), "+f"(d[24]), "+f"(d[25]), "+f"(d[26]), "+f"(d[27]), "+f"(d[28]), "+f"(d[29]), "+f"(d[30]), "+f"(d[31]), "+f"(d[32]), "+f"(d[33]), "+f"(d[34]), "+f"(d[35]), "+f"(d[36]), "+f"(d[37]), "+f"(d[38]), "+f"(d[39]), "+f"(d[40]), "+f"(d[41]), "+f"(d[42]), "+f"(d[43]), "+f"(d[44]), "+f"(d[45]), "+f"(d[46]), "+f"(d[47]), "+f"(d[48]), "+f"(d[49]), "+f"(d[50]), "+f"(d[51]), "+f"(d[52]), "+f"(d[53]), "+f"(d[54]), "+f"(d[55]), "+f"(d[56]), "+f"(d[57]), "+f"(d[58]), "+f"(d[59]), "+f"(d[60]), "+f"(d[61]), "+f"(d[62]), "+f"(d[63]), "+f"(d[64]), "+f"(d[65]), "+f"(d[66]), "+f"(d[67]), "+f"(d[68]), "+f"(d[69]), "+f"(d[70]), "+f"(d[71]), "+f"(d[72]), "+f"(d[73]), "+f"(d[74]), "+f"(d[75]), "+f"(d[76]), "+f"(d[77]), "+f"(d[78]), "+f"(d[79]), "+f"(d[80]), "+f"(d[81]), "+f"(d[82]), "+f"(d[83]), "+f"(d[84]), "+f"(d[85]), "+f"(d[86]), "+f"(d[87]), "+f"(d[88]), "+f"(d[89]), "+f"(d[90]), "+f"(d[91]), "+f"(d[92]), "+f"(d[93]), "+f"(d[94]), "+f"(d[95])
               : "l"(descA), "l"(descB), "n"(scale_d), "n"(tnsp_b));
}
template <int scale_d> __device__ __forceinline__ void wgmma4_n192(float* d, uint32_t da, uint32_t db) {
#define R_ "{%0,%1,%2,%3,%4,%5,%6,%7,%8,%9,%10,%11,%12,%13,%14,%15,%16,%17,%18,%19,%20,%21,%22,%23,%24,%25,%26,%27,%28,%29,%30,%31,%32,%33,%34,%35,%36,%37,%38,%39,%40,%41,%42,%43,%44,%45,%46,%47,%48,%49,%50,%51,%52,%53,%54,%55,%56,%57,%58,%59,%60,%61,%62,%63,%64,%65,%66,%67,%68,%69,%70,%71,%72,%73,%74,%75,%76,%77,%78,%79,%80,%81,%82,%83,%84,%85,%86,%87,%88,%89,%90,%91,%92,%93,%94,%95}"
  asm volatile("{\n.reg .pred p, q;\n.reg .b64 a, b;\nsetp.ne.b32 p, %98, 0;\nsetp.eq.b32 q, 0, 0;\nmov.b64 a, {%96, 0x40000040};\nmov.b64 b, {%97, 0x40000040};\n"
               "wgmma.mma_async.sync.aligned.m64n192k16.f32.bf16.bf16 " R_ ", a, b, p, 1, 1, 0, 1;\nadd.s64 a, a, 2;\nadd.s64 b, b, 128;\n"
               "wgmma.mma_async.sync.aligned.m64n192k16.f32.bf16.bf16 " R_ ", a, b, q, 1, 1, 0, 1;\nadd.s64 a, a, 2;\nadd.s64 b, b, 128;\n"
               "wgmma.mma_async.sync.aligned.m64n192k16.f32.bf16.bf16 " R_ ", a, b, q, 1, 1, 0, 1;\nadd.s64 a, a, 2;\nadd.s64 b, b, 128;\n"
               "wgmma.mma_async.sync.aligned.m64n192k16.f32.bf16.bf16 " R_ ", a, b, q, 1, 1, 0, 1;\n}\n"
               : "+f"(d[0]), "+f"(d[1]), "+f"(d[2]), "+f"(d[3]), "+f"(d[4]), "+f"(d[5]), "+f"(d[6]), "+f"(d[7]), "+f"(d[8]), "+f"(d[9]), "+f"(d[10]), "+f"(d[11]), "+f"(d[12]), "+f"(d[13]), "+f"(d[14]), "+f"(d[15]), "+f"(d[16]), "+f"(d[17]), "+f"(d[18]), "+f"(d[19]), "+f"(d[20]), "+f"(d[21]), "+f"(d[22]), "+f"(d[23]), "+f"(d[24]), "+f"(d[25]), "+f"(d[26]), "+f"(d[27]), "+f"(d[28]), "+f"(d[29]), "+f"(d[30]), "+f"(d[31]), "+f"(d[32]), "+f"(d[33]), "+f"(d[34]), "+f"(d[35]), "+f"(d[36]), "+f"(d[37]), "+f"(d[38]), "+f"(d[39]), "+f"(d[40]), "+f"(d[41]), "+f"(d[42]), "+f"(d[43]), "+f"(d[44]), "+f"(d[45]), "+f"(d[46]), "+f"(d[47]), "+f"(d[48]), "+f"(d[49]), "+f"(d[50]), "+f"(d[51]), "+f"(d[52]), "+f"(d[53]), "+f"(d[54]), "+f"(d[55]), "+f"(d[56]), "+f"(d[57]), "+f"(d[58]), "+f"(d[59]), "+f"(d[60]), "+f"(d[61]), "+f"(d[62]), "+f"(d[63]), "+f"(d[64]), "+f"(d[65]), "+f"(d[66]), "+f"(d[67]), "+f"(d[68]), "+f"(d[69]), "+f"(d[70]), "+f"(d[71]), "+f"(d[72]), "+f"(d[73]), "+f"(d[74]), "+f"(d[75]), "+f"(d[76]), "+f"(d[77]), "+f"(d[78]), "+f"(d[79]), "+f"(d[80]), "+f"(d[81]), "+f"(d[82]), "+f"(d[83]), "+f"(d[84]), "+f"(d[85]), "+f"(d[86]), "+f"(d[87]), "+f"(d[88]), "+f"(d[89]), "+f"(d[90]), "+f"(d[91]), "+f"(d[92]), "+f"(d[93]), "+f"(d[94]), "+f"(d[95])
               : "r"(da), "r"(db), "n"(scale_d));
#undef R_
}
template <int scale_d> __device__ __forceinline__ void wgmma4_n128(float* d, uint32_t da, uint32_t db) {
#define R_ "{%0,%1,%2,%3,%4,%5,%6,%7,%8,%9,%10,%11,%12,%13,%14,%15,%16,%17,%18,%19,%20,%21,%22,%23,%24,%25,%26,%27,%28,%29,%30,%31,%32,%33,%34,%35,%36,%37,%38,%39,%40,%41,%42,%43,%44,%45,%46,%47,%48,%49,%50,%51,%52,%53,%54,%55,%56,%57,%58,%59,%60,%61,%62,%63}"
  asm volatile("{\n.reg .pred p, q;\n.reg .b64 a, b;\nsetp.ne.b32 p, %66, 0;\nsetp.eq.b32 q, 0, 0;\nmov.b64 a, {%64, 0x40000040};\nmov.b64 b, {%65, 0x40000040};\n"
               "wgmma.mma_async.sync.aligned.m64n128k16.f32.bf16.bf16 " R_ ", a, b, p, 1, 1, 0, 1;\nadd.s64 a, a, 2;\nadd.s64 b, b, 128;\n"
               "wgmma.mma_async.sync.aligned.m64n128k16.f32.bf16.bf16 " R_ ", a, b, q, 1, 1, 0, 1;\nadd.s64 a, a, 2;\nadd.s64 b, b, 128;\n"
               "wgmma.mma_async.sync.aligned.m64n128k16.f32.bf16.bf16 " R_ ", a, b, q, 1, 1, 0, 1;\nadd.s64 a, a, 2;\nadd.s64 b, b, 128;\n"
               "wgmma.mma_async.sync.aligned.m64n128k16.f32.bf16.bf16 " R_ ", a, b, q, 1, 1, 0, 1;\n}\n"
               : "+f"(d[0]), "+f"(d[1]), "+f"(d[2]), "+f"(d[3]), "+f"(d[4]), "+f"(d[5]), "+f"(d[6]), "+f"(d[7]), "+f"(d[8]), "+f"(d[9]), "+f"(d[10]), "+f"(d[11]), "+f"(d[12]), "+f"(d[13]), "+f"(d[14]), "+f"(d[15]), "+f"(d[16]), "+f"(d[17]), "+f"(d[18]), "+f"(d[19]), "+f"(d[20]), "+f"(d[21]), "+f"(d[22]), "+f"(d[23]), "+f"(d[24]), "+f"(d[25]), "+f"(d[26]), "+f"(d[27]), "+f"(d[28]), "+f"(d[29]), "+f"(d[30]), "+f"(d[31]), "+f"(d[32]), "+f"(d[33]), "+f"(d[34]), "+f"(d[35]), "+f"(d[36]), "+f"(d[37]), "+f"(d[38]), "+f"(d[39]), "+f"(d[40]), "+f"(d[41]), "+f"(d[42]), "+f"(d[43]), "+f"(d[44]), "+f"(d[45]), "+f"(d[46]), "+f"(d[47]), "+f"(d[48]), "+f"(d[49]), "+f"(d[50]), "+f"(d[51]), "+f"(d[52]), "+f"(d[53]), "+f"(d[54]), "+f"(d[55]), "+f"(d[56]), "+f"(d[57]), "+f"(d[58]), "+f"(d[59]), "+f"(d[60]), "+f"(d[61]), "+f"(d[62]), "+f"(d[63])
               : "r"(da), "r"(db), "n"(scale_d));
#undef R_
}
template <int scale_d> __device__ __forceinline__ void wgmma_n32(float* d, uint64_t descA, uint64_t descB) {
  asm volatile("{\n.reg .pred p;\nsetp.ne.b32 p, %18, 0;\n"
               "wgmma.mma_async.sync.aligned.m64n32k16.f32.bf16.bf16 {%0,%1,%2,%3,%4,%5,%6,%7,%8,%9,%10,%11,%12,%13,%14,%15}, %16, %17, p, 1, 1, 0, 1;\n}\n"
               : "+f"(d[0]), "+f"(d[1]), "+f"(d[2]), "+f"(d[3]), "+f"(d[4]), "+f"(d[5]), "+f"(d[6]), "+f"(d[7]), "+f"(d[8]), "+f"(d[9]), "+f"(d[10]), "+f"(d[11]), "+f"(d[12]), "+f"(d[13]), "+f"(d[14]), "+f"(d[15])
               : "l"(descA), "l"(descB), "n"(scale_d));
}
template <int scale_d, int tnsp_a> __device__ __forceinline__ void wgmma_n40(float* d, uint64_t descA, uint64_t descB) {
  asm volatile("{\n.reg .pred p;\nsetp.ne.b32 p, %22, 0;\n"
               "wgmma.mma_async.sync.aligned.m64n40k16.f32.bf16.bf16 {%0,%1,%2,%3,%4,%5,%6,%7,%8,%9,%10,%11,%12,%13,%14,%15,%16,%17,%18,%19}, %20, %21, p, 1, 1, %23, 1;\n}\n"
               : "+f"(d[0]), "+f"(d[1]), "+f"(d[2]), "+f"(d[3]), "+f"(d[4]), "+f"(d[5]), "+f"(d[6]), "+f"(d[7]), "+f"(d[8]), "+f"(d[9]), "+f"(d[10]), "+f"(d[11]), "+f"(d[12]), "+f"(d[13]), "+f"(d[14]), "+f"(d[15]), "+f"(d[16]), "+f"(d[17]), "+f"(d[18]), "+f"(d[19])
               : "l"(descA), "l"(descB), "n"(scale_d), "n"(tnsp_a));
}
template <int scale_d> __device__ __forceinline__ void wgmma_n40_rs(float* d, const uint32_t* a, uint64_t descB) {
  asm volatile("{\n.reg .pred p;\nsetp.ne.b32 p, %25, 0;\n"
               "wgmma.mma_async.sync.aligned.m64n40k16.f32.bf16.bf16 {%0,%1,%2,%3,%4,%5,%6,%7,%8,%9,%10,%11,%12,%13,%14,%15,%16,%17,%18,%19}, {%20,%21,%22,%23}, %24, p, 1, 1, 1;\n}\n"
               : "+f"(d[0]), "+f"(d[1]), "+f"(d[2]), "+f"(d[3]), "+f"(d[4]), "+f"(d[5]), "+f"(d[6]), "+f"(d[7]), "+f"(d[8]), "+f"(d[9]), "+f"(d[10]), "+f"(d[11]), "+f"(d[12]), "+f"(d[13]), "+f"(d[14]), "+f"(d[15]), "+f"(d[16]), "+f"(d[17]), "+f"(d[18]), "+f"(d[19])
               : "r"(a[0]), "r"(a[1]), "r"(a[2]), "r"(a[3]), "l"(descB), "n"(scale_d));
}
__device__ __forceinline__ void wgmma_copy(float* d, uint32_t da, uint64_t descB) {
  asm volatile("{\n.reg .pred p;\n.reg .b64 a;\nsetp.ne.b32 p, 0, 0;\nmov.b64 a, {%64, 0x40000040};\n"
               "wgmma.mma_async.sync.aligned.m64n16k16.f32.bf16.bf16 {%0,%1,%2,%3,%4,%5,%6,%7}, a, %65, p, 1, 1, 0, 0;\nadd.s64 a, a, 2;\n"
               "wgmma.mma_async.sync.aligned.m64n16k16.f32.bf16.bf16 {%8,%9,%10,%11,%12,%13,%14,%15}, a, %65, p, 1, 1, 0, 0;\nadd.s64 a, a, 2;\n"
               "wgmma.mma_async.sync.aligned.m64n16k16.f32.bf16.bf16 {%16,%17,%18,%19,%20,%21,%22,%23}, a, %65, p, 1, 1, 0, 0;\nadd.s64 a, a, 2;\n"
               "wgmma.mma_async.sync.aligned.m64n16k16.f32.bf16.bf16 {%24,%25,%26,%27,%28,%29,%30,%31}, a, %65, p, 1, 1, 0, 0;\nadd.s64 a, a, 1018;\n"
               "wgmma.mma_async.sync.aligned.m64n16k16.f32.bf16.bf16 {%32,%33,%34,%35,%36,%37,%38,%39}, a, %65, p, 1, 1, 0, 0;\nadd.s64 a, a, 2;\n"
               "wgmma.mma_async.sync.aligned.m64n16k16.f32.bf16.bf16 {%40,%41,%42,%43,%44,%45,%46,%47}, a, %65, p, 1, 1, 0, 0;\nadd.s64 a, a, 2;\n"
               "wgmma.mma_async.sync.aligned.m64n16k16.f32.bf16.bf16 {%48,%49,%50,%51,%52,%53,%54,%55}, a, %65, p, 1, 1, 0, 0;\nadd.s64 a, a, 2;\n"
               "wgmma.mma_async.sync.aligned.m64n16k16.f32.bf16.bf16 {%56,%57,%58,%59,%60,%61,%62,%63}, a, %65, p, 1, 1, 0, 0;\n"
               "}\n"
               : "+f"(d[0]), "+f"(d[1]), "+f"(d[2]), "+f"(d[3]), "+f"(d[4]), "+f"(d[5]), "+f"(d[6]), "+f"(d[7]), "+f"(d[8]), "+f"(d[9]), "+f"(d[10]), "+f"(d[11]), "+f"(d[12]), "+f"(d[13]), "+f"(d[14]), "+f"(d[15]), "+f"(d[16]), "+f"(d[17]), "+f"(d[18]), "+f"(d[19]), "+f"(d[20]), "+f"(d[21]), "+f"(d[22]), "+f"(d[23]), "+f"(d[24]), "+f"(d[25]), "+f"(d[26]), "+f"(d[27]), "+f"(d[28]), "+f"(d[29]), "+f"(d[30]), "+f"(d[31]), "+f"(d[32]), "+f"(d[33]), "+f"(d[34]), "+f"(d[35]), "+f"(d[36]), "+f"(d[37]), "+f"(d[38]), "+f"(d[39]), "+f"(d[40]), "+f"(d[41]), "+f"(d[42]), "+f"(d[43]), "+f"(d[44]), "+f"(d[45]), "+f"(d[46]), "+f"(d[47]), "+f"(d[48]), "+f"(d[49]), "+f"(d[50]), "+f"(d[51]), "+f"(d[52]), "+f"(d[53]), "+f"(d[54]), "+f"(d[55]), "+f"(d[56]), "+f"(d[57]), "+f"(d[58]), "+f"(d[59]), "+f"(d[60]), "+f"(d[61]), "+f"(d[62]), "+f"(d[63])
               : "r"(da), "l"(descB));
}
__device__ __forceinline__ uint64_t make_desc(uint32_t addr, uint32_t lbo_bytes, uint32_t sbo_bytes) {
  return (uint64_t)((addr & 0x3FFFF) >> 4) | ((uint64_t)(lbo_bytes >> 4) << 16) | ((uint64_t)(sbo_bytes >> 4) << 32) | (1ull << 62);
}

__device__ __forceinline__ void ldsm_x4(uint32_t addr, uint32_t& r0, uint32_t& r1, uint32_t& r2, uint32_t& r3) {
  asm volatile("ldmatrix.sync.aligned.m8n8.x4.shared.b16 {%0,%1,%2,%3}, [%4];" : "=r"(r0), "=r"(r1), "=r"(r2), "=r"(r3) : "r"(addr) : "memory");
}
__device__ __forceinline__ void ldsm_x4_t(uint32_t addr, uint32_t& r0, uint32_t& r1, uint32_t& r2, uint32_t& r3) {
  asm volatile("ldmatrix.sync.aligned.m8n8.x4.trans.shared.b16 {%0,%1,%2,%3}, [%4];" : "=r"(r0), "=r"(r1), "=r"(r2), "=r"(r3) : "r"(addr) : "memory");
}
__device__ __forceinline__ void stsm_x4(uint32_t addr, uint32_t r0, uint32_t r1, uint32_t r2, uint32_t r3) {
  asm volatile("stmatrix.sync.aligned.m8n8.x4.shared.b16 [%0], {%1,%2,%3,%4};" :: "r"(addr), "r"(r0), "r"(r1), "r"(r2), "r"(r3) : "memory");
}
__device__ __forceinline__ void sts128(uint32_t addr, uint32_t a, uint32_t b, uint32_t c, uint32_t d) {
  asm volatile("st.shared.v4.u32 [%0], {%1,%2,%3,%4};" :: "r"(addr), "r"(a), "r"(b), "r"(c), "r"(d) : "memory");
}
__device__ __forceinline__ float lds32f(uint32_t addr) {
  float v;
  asm volatile("ld.shared.f32 %0, [%1];" : "=f"(v) : "r"(addr) : "memory");
  return v;
}
__device__ __forceinline__ void sts32f(uint32_t addr, float a) {
  asm volatile("st.shared.f32 [%0], %1;" :: "r"(addr), "f"(a) : "memory");
}
__device__ __forceinline__ void mma_bf16(float (&c)[4], uint32_t a0, uint32_t a1, uint32_t a2, uint32_t a3, uint32_t b0, uint32_t b1) {
  asm volatile("mma.sync.aligned.m16n8k16.row.col.f32.bf16.bf16.f32 {%0,%1,%2,%3}, {%4,%5,%6,%7}, {%8,%9}, {%0,%1,%2,%3};"
               : "+f"(c[0]), "+f"(c[1]), "+f"(c[2]), "+f"(c[3]) : "r"(a0), "r"(a1), "r"(a2), "r"(a3), "r"(b0), "r"(b1));
}
__device__ __forceinline__ void mma_bf16_z(float (&c)[4], uint32_t a0, uint32_t a1, uint32_t a2, uint32_t a3, uint32_t b0, uint32_t b1) {
  asm volatile("mma.sync.aligned.m16n8k16.row.col.f32.bf16.bf16.f32 {%0,%1,%2,%3}, {%4,%5,%6,%7}, {%8,%9}, {%10,%10,%10,%10};"
               : "=f"(c[0]), "=f"(c[1]), "=f"(c[2]), "=f"(c[3]) : "r"(a0), "r"(a1), "r"(a2), "r"(a3), "r"(b0), "r"(b1), "f"(0.f));
}
__device__ __forceinline__ uint32_t movm_t(uint32_t v) {
  uint32_t r;
  asm volatile("movmatrix.sync.aligned.m8n8.trans.b16 %0, %1;" : "=r"(r) : "r"(v));
  return r;
}
__device__ __forceinline__ uint32_t pack_bf16(float lo, float hi) {
  uint32_t r;
  asm("cvt.rn.bf16x2.f32 %0, %1, %2;" : "=r"(r) : "f"(hi), "f"(lo));
  return r;
}
__device__ __forceinline__ float bf_lo(uint32_t v) { return __uint_as_float(v << 16); }
__device__ __forceinline__ float bf_hi(uint32_t v) { return __uint_as_float(v & 0xFFFF0000u); }
__device__ __forceinline__ void split3(float x, uint32_t& h, uint32_t& m, uint32_t& l) {
  h = pack_bf16(x, 0.f); x -= bf_lo(h);
  m = pack_bf16(x, 0.f); x -= bf_lo(m);
  l = pack_bf16(x, 0.f);
}
__device__ __forceinline__ float ex2(float x) { float r; asm("ex2.approx.ftz.f32 %0, %1;" : "=f"(r) : "f"(x)); return r; }
__device__ __forceinline__ float rcp_fast(float x) { float r; asm("rcp.approx.ftz.f32 %0, %1;" : "=f"(r) : "f"(x)); return r; }
__device__ __forceinline__ void red_v4(float* p, float a, float b, float c, float d) {
  asm volatile("red.global.add.v4.f32 [%0], {%1, %2, %3, %4};" :: "l"(p), "f"(a), "f"(b), "f"(c), "f"(d) : "memory");
}
__device__ __forceinline__ uint4 ld_ll(const uint4* p) {
  uint4 v;
  asm volatile("{\n.reg .b64 a, b;\nld.relaxed.gpu.global.v2.b64 {a, b}, [%4];\nmov.b64 {%0, %1}, a;\nmov.b64 {%2, %3}, b;\n}\n"
               : "=r"(v.x), "=r"(v.y), "=r"(v.z), "=r"(v.w) : "l"(p) : "memory");
  return v;
}
__device__ __forceinline__ void st_b64(uint2* p, uint32_t a, uint32_t b) {
  asm volatile("{\n.reg .b64 v;\nmov.b64 v, {%1, %2};\nst.relaxed.gpu.global.b64 [%0], v;\n}\n" :: "l"(p), "r"(a), "r"(b) : "memory");
}
__device__ __forceinline__ void st_b128(uint4* p, uint32_t a, uint32_t b, uint32_t c, uint32_t d) {
  asm volatile("{\n.reg .b128 v;\nmov.b128 v, {%1, %2, %3, %4};\nst.relaxed.gpu.global.b128 [%0], v;\n}\n" :: "l"(p), "r"(a), "r"(b), "r"(c), "r"(d) : "memory");
}
__device__ __forceinline__ uint4 ld_b128(const uint4* p) {
  uint4 v;
  asm volatile("{\n.reg .b128 v;\nld.relaxed.gpu.global.b128 v, [%4];\nmov.b128 {%0, %1, %2, %3}, v;\n}\n" : "=r"(v.x), "=r"(v.y), "=r"(v.z), "=r"(v.w) : "l"(p) : "memory");
  return v;
}

constexpr float LOG2E = 1.4426950408889634f;

struct Params {
  const __nv_bfloat16* x0;
  const __nv_bfloat16* wA_qkv;
  const __nv_bfloat16* wA_o;
  const __nv_bfloat16* wB_qkv;
  const __nv_bfloat16* wB_phi;
  const __nv_bfloat16* wB_o;
  __nv_bfloat16* out;
};

#define ACC_DEF(d, n) _Pragma("unroll") for (int i_ = 0; i_ < (n); i_++) asm volatile("" : "=f"(d[i_]))
#define ACC_FENCE(d, n) _Pragma("unroll") for (int i_ = 0; i_ < (n); i_++) asm volatile("" : "+f"(d[i_]) :: "memory")
#define PIN(a, n) _Pragma("unroll") for (int i_ = 0; i_ < (n); i_++) asm volatile("" : "+f"((a)[i_]))
#define PINU(a, n) _Pragma("unroll") for (int i_ = 0; i_ < (n); i_++) asm volatile("" : "+r"((a)[i_]))

#define V_ADDR(p0, sw) uint32_t va_[2] = {(p0) + (srowoff >> 1) + (lhi ^ lsw2 ^ (sw)), (p0) + (srowoff >> 1) + ((32 + lhi) ^ lsw2 ^ (sw))}
#define STAGE_V(acc) { \
    _Pragma("unroll") for (int j_ = 0; j_ < 4; j_++) { \
      const float* a_ = (acc) + j_ * 8; \
      stsm_x4(va_[j_ & 1] + (j_ >> 1) * 8192, \
              pack_bf16(rs0 * a_[0], rs0 * a_[1]), pack_bf16(rs1 * a_[2], rs1 * a_[3]), pack_bf16(rs0 * a_[4], rs0 * a_[5]), pack_bf16(rs1 * a_[6], rs1 * a_[7])); } }
#define FRAG(dst, acc, TR, grp) { \
    _Pragma("unroll") for (int i_ = 0; i_ < 16; i_++) { \
      const float r_ = (i_ & 1) ? rs1 : rs0; \
      const uint32_t w_ = pack_bf16(r_ * (acc)[2 * i_], r_ * (acc)[2 * i_ + 1]); \
      if (TR) (dst)[i_] = movm_t(w_); else (dst)[(i_ & 12) + (i_ & 1) * 2 + ((i_ >> 1) & 1)] = w_; } \
    if (warp == 7 && mm < 15) { \
      _Pragma("unroll") for (int j_ = 0; j_ < 4; j_++) \
        st_b128(g_halo + (size_t)(mm * 8 + jj) * 512 + ((grp) * 4 + j_) * 32 + lane, ((dst)[j_ * 4] & ~1u) | H_BIT(l), (dst)[j_ * 4 + 1], (dst)[j_ * 4 + 2], (dst)[j_ * 4 + 3]); } \
    PINU(dst, 16); }
#define FRAG_PUT(src, slot) if (warp < 7) { _Pragma("unroll") for (int j_ = 0; j_ < 4; j_++) \
      sts128(sbase + (slot) * SLOT + 2048 + warp * 2048 + j_ * 512 + lane * 16, (src)[j_ * 4], (src)[j_ * 4 + 1], (src)[j_ * 4 + 2], (src)[j_ * 4 + 3]); }
#define FRAG_GET(dst, slot) { _Pragma("unroll") for (int j_ = 0; j_ < 4; j_++) \
      asm volatile("ld.shared.v4.u32 {%0, %1, %2, %3}, [%4];" : "=r"((dst)[j_ * 4]), "=r"((dst)[j_ * 4 + 1]), "=r"((dst)[j_ * 4 + 2]), "=r"((dst)[j_ * 4 + 3]) \
                   : "r"(sbase + (slot) * SLOT + warp * 2048 + j_ * 512 + lane * 16) : "memory"); }
#define RW(j) (((j) >> 1) * 4 + ((j) & 1))
template <int POS> __device__ __forceinline__ float exps16_(float* o, const float* p) {
  float s[4];
#pragma unroll
  for (int j = 0; j < 16; j++) { o[j] = ex2(POS ? p[RW(j)] : -p[RW(j)]); if (j < 4) s[j] = o[j]; else s[j & 3] += o[j]; }
  const float r = (s[0] + s[1]) + (s[2] + s[3]);
  return r + __shfl_xor_sync(0xffffffffu, r, 1);
}
template <int POS> __device__ __forceinline__ void exps16_fix(float* o, const float* p, float& sum) {
  if (__builtin_expect(__any_sync(0xffffffffu, !(sum > SUMLO && sum < SUMHI)), 0)) {
    float m = p[0], q[32];
#pragma unroll
    for (int j = 1; j < 16; j++) m = POS ? fmaxf(m, p[RW(j)]) : fminf(m, p[RW(j)]);
    const float x = __shfl_xor_sync(0xffffffffu, m, 1);
    m = POS ? fmaxf(m, x) : fminf(m, x);
#pragma unroll
    for (int j = 0; j < 16; j++) q[RW(j)] = p[RW(j)] - m;
    sum = exps16_<POS>(o, q);
  }
}
__device__ __forceinline__ void store16(const float* e, float sum, uint32_t dst, uint32_t dsw, int c0) {
  const float inv = rcp_fast(sum);
#pragma unroll
  for (int j = 0; j < 2; j++)
    sts128(dst + (((c0 + j) << 4) ^ dsw), pack_bf16(e[j * 8] * inv, e[j * 8 + 1] * inv), pack_bf16(e[j * 8 + 2] * inv, e[j * 8 + 3] * inv),
           pack_bf16(e[j * 8 + 4] * inv, e[j * 8 + 5] * inv), pack_bf16(e[j * 8 + 6] * inv, e[j * 8 + 7] * inv));
}
template <int POS> __device__ __forceinline__ void expp16(uint32_t* o, float* p) {
  {
#pragma unroll
    for (int r = 0; r < 4; r += 2) {
      float m = p[r];
#pragma unroll
      for (int j = 1; j < 8; j++) m = POS ? fmaxf(m, p[r + RW(j)]) : fminf(m, p[r + RW(j)]);
#pragma unroll
      for (int s = 1; s <= 2; s <<= 1) { const float x = __shfl_xor_sync(0xffffffffu, m, s); m = POS ? fmaxf(m, x) : fminf(m, x); }
#pragma unroll
      for (int j = 0; j < 8; j++) p[r + RW(j)] -= m;
    }
  }
#pragma unroll
  for (int j = 0; j < 8; j++) o[j] = pack_bf16(ex2(POS ? p[2 * j] : -p[2 * j]), ex2(POS ? p[2 * j + 1] : -p[2 * j + 1]));
}
__device__ __forceinline__ void scale32(float* o, const float* p, float c0, float c1) {
#pragma unroll
  for (int i = 0; i < 32; i++) asm volatile("mul.f32 %0, %1, %2;" : "=f"(o[i]) : "f"(p[i]), "f"((i & 2) ? c1 : c0));
}
__device__ __forceinline__ bool any_big(const float* p) {
  float m[4];
#pragma unroll
  for (int i = 0; i < 32; i++) m[i >> 3] = (i & 7) ? fmaf(p[i], p[i], m[i >> 3]) : p[i] * p[i];
  return __any_sync(0xffffffffu, !(fmaxf(fmaxf(m[0], m[1]), fmaxf(m[2], m[3])) < BIGLIM));
}
__device__ __forceinline__ void phiq_a(float* p, bool big) {
  if (__builtin_expect(!big, 1)) {
#pragma unroll
    for (int j = 0; j < 16; j++) p[j] = ex2(p[j]);
  }
}
template <int NEXT> __device__ __forceinline__ void phiq_b(uint32_t* o, float* p, bool big) {
  if (__builtin_expect(big, 0)) {
    expp16<0>(o, p); expp16<1>(o + 8, p);
  } else {
    if (NEXT) phiq_a(p + 16, false);
#pragma unroll
    for (int j = 0; j < 4; j++) {
      const float a = p[4 * j], b = p[4 * j + 1], c = p[4 * j + 2], d = p[4 * j + 3];
      const float ab = a * b, cd = c * d, r = rcp_fast(ab * cd), x = r * cd, y = r * ab;
      o[2 * j] = pack_bf16(x * b, x * a); o[2 * j + 1] = pack_bf16(y * d, y * c);
      o[8 + 2 * j] = pack_bf16(a, b); o[9 + 2 * j] = pack_bf16(c, d);
    }
  }
}
#define SCHED_FENCE() asm volatile("pmevent 0;" ::: "memory")

__global__ void __cluster_dims__(2, 1, 1) __launch_bounds__(384, 1)
mega_kernel(const __grid_constant__ CUtensorMap tm_x0, const __grid_constant__ CUtensorMap tm_xo, const __grid_constant__ CUtensorMap tm_os,
            const __grid_constant__ CUtensorMap tm_o, const __grid_constant__ CUtensorMap tm_wf,
            const __grid_constant__ CUtensorMap tm_wqA, const __grid_constant__ CUtensorMap tm_wqB,
            const __grid_constant__ CUtensorMap tm_woA, const __grid_constant__ CUtensorMap tm_woB,
            const __grid_constant__ CUtensorMap tm_phi, const Params prm) {
  extern __shared__ __align__(1024) uint8_t smem_raw[];
  const uint32_t sbase = smem_u32(smem_raw);
  const uint32_t bar_full = sbase + OFF_BAR;
  const uint32_t bar_done = bar_full + 384;
  const uint32_t bar_stat = bar_full + 768, bar_stat2 = bar_full + 776, bar_epi = bar_full + 784, bar_phi = bar_full + 936  , bar_halo = bar_full + 904  ;
  const uint32_t bar_xr = bar_full + 800, bar_lx = bar_full + 808, bar_stg = bar_full + 832;
  const uint32_t bar_chk = bar_full + 848;

  const int warp = __shfl_sync(0xffffffffu, threadIdx.x >> 5, 0), lane = threadIdx.x & 31;
  const uint32_t bar_kx = sbase + OFF_ID + 384 + warp * 8;
  uint32_t rank;
  asm volatile("mov.u32 %0, %%cluster_ctarank;" : "=r"(rank));
  const int aux = (int)blockIdx.x - NMAIN, tp = (int)(blockIdx.x >> 1) - 4;
  const int gp = tp < 0 ? 0 : (tp < 32 ? tp & 7 : 1 + (tp - 32) % 7), me = tp < 0 ? tp + 8 : (tp < 32 ? tp >> 3 : 4 + (tp - 32) / 7);
  const int jj = me, cc = gp;
  const int cta = aux >= 0 ? -1 : (cc * 8 + jj) * 2 + (int)rank;
  const int mm = cc * 2 + (int)rank;

#define LOAD_EPOCH() const unsigned epoch = ld_relaxed(&g_flags.epoch.v), ep1 = epoch + 1; (void)epoch
  int budget = 1 << 22;

  if (cta >= 0) {
    if (warp >= 8 && warp < 8 + EARLY && elect_one()) {
      const int u = warp - 8;
      const uint32_t fb = bar_full + u * 8;
      mbar_init(fb, 1);
      asm volatile("fence.mbarrier_init.release.cluster;" ::: "memory");
      fence_proxy_async_smem();
      mbar_expect_tx(fb, QST + SLOT);
      if (u) __nanosleep(STAG2);
      tma_load_2d(sbase + OFF_S + u * SLOT, &tm_x0, fb, jj * 128 + u * 64, mm * 128);
#pragma unroll
      for (int i = 0; i < 6; i++) tma_load_2d(sbase + u * QST + i * 4096, &tm_wqA, fb, jj * 128 + (i >> 1) * 1024, jj * 128 + u * 64 + (i & 1) * 32);
      if (u == 0) PROFT(472);
    }
    __syncwarp();
    {
      const int tx = threadIdx.x;
      const __nv_bfloat16* pf = (tx < 128) ? prm.x0 + (size_t)(mm * 128 + tx) * D_MODEL + jj * 128
                                           : prm.wA_qkv + (size_t)(jj * 128 + (tx & 63)) * 3072 + ((tx - 128) >> 6) * 1024 + jj * 128 + rank * 64;
      if (tx < 320) asm volatile("prefetch.global.L2 [%0];" :: "l"(pf));
      else if (tx == 320) prefetch_tmap(&tm_x0);
      else if (tx == 352) prefetch_tmap(&tm_wqA);
      else if (tx == 383) asm volatile("prefetch.global.L2 [%0];" :: "l"(&g_flags.epoch.v));
    }
    if (elect_one()) {
#pragma unroll
      for (int i = 0; i < 4; i++) {
        const int u = warp * 4 + i;
        if (u >= EARLY) mbar_init(bar_full + u * 8, ((u >= 4 && u < 11) || (u > 32 && u != 40)) ? 2 : 1); mbar_init(bar_done + u * 8, 16);
      }
      mbar_init(bar_stat + warp * 16, 0x111111181182ull >> (4 * warp) & 15);
      mbar_init(bar_stat + warp * 16 + 8, 0x111111121811ull >> (4 * warp) & 15);
      mbar_init(bar_chk + 112 + (warp & 7) * 8, 1);
      mbar_init(bar_kx, 1);
      asm volatile("fence.mbarrier_init.release.cluster;" ::: "memory");
    }
    __syncwarp();
    __syncthreads();
    asm volatile("barrier.cluster.arrive.relaxed.aligned;" ::: "memory");
  }

  if (cta < 0) {
    LOAD_EPOCH();
    const uint32_t buf = sbase + warp * SLOT, bar = sbase + OFF_BAR + warp * 16;
    const uint32_t lsw = (lane & 7) << 4, lhi = (lane >> 4) << 4, lrow = (lane & 15) * 128;
    const bool el = elect_one();
    if (el) {
      mbar_init(bar, 1); mbar_init(bar + 8, 1);
      asm volatile("fence.mbarrier_init.release.cluster;" ::: "memory");
    }
#pragma unroll 1
    for (int rd = 0; rd < (NLAYERS > 1 ? 5 : 2); rd++) {
      if (rd >= 2 && warp >= 8) break;
      const int tk = rd < 2 ? aux * 12 + warp : aux * 8 + warp;
      const int half = tk & 1;
      const int blk = rd < 2 ? (tk >> 1) * 2 + rd : (4 - rd) * 16 + (tk >> 1);
      const CUtensorMap* tm = rd < 2 ? &tm_wqA : (rd == 2 ? &tm_wqB : &tm_wf);
      const int j0 = (blk & 15) >> 1;
#define AUX_LOAD(n) { const uint32_t d_ = buf + ((n) & 1) * 8192, b_ = bar + ((n) & 1) * 8; const int r_ = kslice(j0, 2 * (n) + half) * 64; \
        mbar_expect_tx(b_, 8192); tma_load_2d(d_, tm, b_, blk * 64, r_); tma_load_2d(d_ + 4096, tm, b_, blk * 64, r_ + 32); }
      if (el) {
        if (rd == 3) { wait_flag(&g_flags.wfready[j0].v, ep1 * 16); fence_proxy_async_global(); }
        AUX_LOAD(0); AUX_LOAD(1);
      }
      __syncwarp();
      float cs[8][4];
#pragma unroll
      for (int i = 0; i < 8; i++) cs[i][0] = cs[i][1] = cs[i][2] = cs[i][3] = 0.f;
#pragma unroll 1
      for (int n = 0; n < 8; n++) {
        const uint32_t tb = buf + (n & 1) * 8192 + lrow;
        mbar_wait(bar + (n & 1) * 8, (n >> 1) & 1);
#pragma unroll
        for (int i = 0; i < 16; i++) {
          uint32_t b0, b1, b2, b3;
          ldsm_x4_t(tb + (i >> 2) * 2048 + (((i & 3) * 32 + lhi) ^ lsw), b0, b1, b2, b3);
          mma_bf16(cs[2 * (i & 3)], 0x3F803F80u, 0x3F803F80u, 0x3F803F80u, 0x3F803F80u, b0, b1);
          mma_bf16(cs[2 * (i & 3) + 1], 0x3F803F80u, 0x3F803F80u, 0x3F803F80u, 0x3F803F80u, b2, b3);
        }
        __syncwarp();
        if (el && n < 6) AUX_LOAD(n + 2);
        __syncwarp();
      }
      if (lane < 4) {
#pragma unroll
        for (int i = 0; i < 8; i++) st_b64(&g_colsum[rd >= 2][blk * 32 + i * 4 + lane][half], __float_as_uint(cs[i][0]), (__float_as_uint(cs[i][1]) & ~3u) | (ep1 & 3));
      }
      __syncwarp();
    }
  } else if (warp >= 8) {
    asm volatile("setmaxnreg.dec.sync.aligned.u32 40;");
    if (warp == 8) {
      const bool el = elect_one();
      cluster_wait();
      if (el) {
#pragma unroll 1
        for (int l = 0; l < NLAYERS; l++) {
          const uint32_t par = l & 1;
          const CUtensorMap* tqk = par ? &tm_wf : &tm_wqA;
          const CUtensorMap* tv = par ? &tm_wqB : &tm_wqA;
          const CUtensorMap* two = par ? &tm_woB : &tm_woA;
          if (l == 1) { LOAD_EPOCH(); wait_flag(&g_flags.wfready[jj].v, ep1 * 16); fence_proxy_async_global(); }
#pragma unroll 1
          for (int u = l ? 0 : EARLY; u < 32; u++) {
            if (u >= 4) mbar_wait_sl(bar_done + (u - 4) * 8, par);
            else if (l) mbar_wait_sl(bar_done + (43 + u + (u >> 1)) * 8, par ^ 1);
            else mbar_wait_sl(bar_full, 0);
            const uint32_t fb = bar_full + u * 8;
            const bool res = u < 11 || (u >= 18 && u < 22);
            mbar_expect_tx(fb, res ? QST : QST + SLOT);
            const int row = kslice(jj, u < 4 ? u & 1 : (u < 18 ? u - 2 : (u < 22 ? u - 6 : u - 20))) * 64 + (int)rank * 32;
            const int ps = u < 4 ? u >> 1 : (u >= 18), col = jj * 128 + ps * 64;
            const int c0 = par ? jj * 128 + (ps ? 0 : 1024) : col;
            const uint32_t dst = sbase + (u & 3) * QST + rank * 4096;
            tma_load_2d_mc(dst, tqk, fb, c0, row);
            tma_load_2d_mc(dst + 8192, tqk, fb, c0 + (par ? 64 : 1024), row);
            tma_load_2d_mc(dst + 16384, tv, fb, col + 2048, row);
            if (l == PRL && u >= PRU && u < PRU + 4) PROFT(473 + u - PRU);
          }
#pragma unroll 1
          for (int s = 0; s < 16; s++) {
            if (s < 5) { if (s != 2 && s != 4) mbar_wait_sl(bar_done + (28 + s) * 8, par); }
            else if (s != 14) mbar_wait_sl(bar_done + (27 + s - (s == 15)) * 8, par);
            const uint32_t fb = bar_full + (32 + s) * 8;
            mbar_expect_tx(fb, SLOT);
            tma_load_2d_mc(sbase + rank * 8192 + (uint32_t)((WO_BSLOT >> (4 * s)) & 15) * SLOT, two, fb, jj * 128 + (int)rank * 64, wslice(jj, s) * 64);
            const int ts = s + par;
            if (s >= 5 && ts < 8) {
              mbar_expect_tx(bar_chk - 8 + ts * 8, SLOT);
              tma_load_2d(sbase + (uint32_t)((WO_ASLOT(par) >> (4 * ts)) & 15) * SLOT, &tm_o, bar_chk - 8 + ts * 8, wslice(jj, ts) * 64, mm * 128);
            }
          }
        }
      }
      __syncwarp();
    } else if (warp == 9) {
      const bool el = elect_one();
      LOAD_EPOCH();
#pragma unroll 1
      for (int lp = 0; lp < 4 * NLAYERS; lp++) {
        const int l = lp >> 2, ph = lp & 3;
        if (ph == 3) continue;
        const uint32_t par = l & 1;
        const unsigned* pp = reinterpret_cast<const unsigned*>(g_obuf + (ph >> 1) * 64 + (size_t)(mm * 128 + (ph ? 0 : S_LEN) + ((lane & 7) | PROWS) * 16 + (jj & 1) * 8) * D_MODEL +
                                                               (jj >> 1) * 16 + srcb(jj, lane >> 3) * 128);
        const CUtensorMap* tm = lp ? &tm_o : &tm_x0;
        const int row = mm * 128 + ((ph || !l) ? 0 : S_LEN);
        const uint32_t bit = ph ? O_BIT(l) : X_BIT(l - 1);
        const uint32_t slots = ph ? (uint32_t)(WO_ASLOT(par) >> (ph * 32 - 28)) : 0x8769876u;
        const unsigned long long fr = ph == 0 ? XPACE : ph == 1 ? (par ? FRB : 0x35351F1Eull) : (par ? 0x27262524232232ull : 0x27262524233232ull);
        uint32_t no = (lp == 0 || (lp & 7) == 1) ? 0 : (ph == 1 ? NOB : (ph ? NO1 : NOX)), v0 = 0, v1 = 0;
        mbar_wait_sl(ph ? bar_done + ((uint32_t)fr & 63) * 8 : (l ? bar_done + 47 * 8 : bar_full), ph ? par : (l ? par ^ 1 : 0));
        if (el && ph) PROFT(324 + l * 16 + ph);
        __syncwarp();
        if (no && (ph == 1 ? SPD1 : (ph ? SPD2 : SPD0))) __nanosleep(ph == 1 ? SPD1 : (ph ? SPD2 : SPD0));
        if (no) { v0 = ld_relaxed(pp); __nanosleep(POLLGAP); v1 = ld_relaxed(pp); }
#pragma unroll 1
        for (int i = 0; i < (ph == 1 ? 4 + par : 7); i++, no >>= 8) {
#pragma unroll 1
          for (int it = 0; (no & 0xFF) && it < (1 << 18); it++) {
            no &= __ballot_sync(0xffffffffu, (v0 ^ bit) & 1) >> (8 * i);
            if (no) v0 = ld_relaxed(pp);
            if (!(no & 0xFF)) break;
            no &= __ballot_sync(0xffffffffu, (v1 ^ bit) & 1) >> (8 * i);
            if (no) v1 = ld_relaxed(pp);
          }
          if (ph || i >= XP0) mbar_wait_sl(bar_done + ((uint32_t)(fr >> (8 * i)) & 63) * 8, par);
          if (el) {
            if (i == 0) PROFT(320 + l * 16 + ph);
            const uint32_t cb = (lp ? bar_chk + (ph >> 1) * 112 : bar_full + 32) + i * 8;
            mbar_expect_tx(cb, SLOT);
            tma_load_2d(sbase + ((slots >> (4 * i)) & 15) * SLOT, tm, cb, srcb(jj, i) * 128 + (ph >> 1) * 64, row);
          }
          __syncwarp();
        }
        if (ph == 0 && el) {
          if (l) { wait_flag(&g_flags.xready[l][mm].v, ep1 * 8); fence_proxy_async_global(); }
#pragma unroll 1
          for (int u = 11; u < 34; u++) {
            if (u == 18) u = 22;
            mbar_wait_sl(bar_done + (u - 4) * 8, par);
            if (u == 32) mbar_expect_tx(bar_xr, 2 * SLOT);
            tma_load_2d(sbase + OFF_RA + (u & 3) * SLOT, tm, u < 32 ? bar_full + u * 8 : bar_xr, kslice(jj, u < 18 ? u - 2 : (u < 32 ? u - 20 : u - 32)) * 64, row);
          }
        }
        __syncwarp();
      }
      if (el && atomicAdd(&g_flags.done.v, 1) == ep1 * NMAIN - 1) asm volatile("st.relaxed.gpu.global.u32 [%0], %1;" :: "l"(&g_flags.epoch.v), "r"(ep1) : "memory");
      __syncwarp();
      cluster_wait();
    } else {
      const int hw = warp - 10;
      LOAD_EPOCH();
      const bool el = elect_one();
      cluster_wait();
      if (hw == 0) {
        mbar_wait_sl(bar_full + 8, 0);
        if (lane < 7) prefetch_tmap(lane == 0 ? &tm_os : lane == 1 ? &tm_o : lane == 2 ? &tm_wf : lane == 3 ? &tm_wqB : lane == 4 ? &tm_woA : lane == 5 ? &tm_woB : &tm_phi);
#pragma unroll 1
        for (int i = 0; i < (NLAYERS > 1 ? 9 : 0); i++) {
          if (i == 0 || i == 5) mbar_wait_sl(bar_done + (i ? FD1 : FD0) * 8, 0);
          if (el) {
            if (i == 0) { mbar_expect_tx(bar_phi, 2 * SLOT + 8192); tma_load_2d(sbase + OFF_PHI, &tm_phi, bar_phi, 0, jj * 128); }
            else tma_load_2d(sbase + (i > 4 ? 10 : 12) * SLOT - 4096 + i * 4096, &tm_wqB, bar_phi, (i > 4 ? 896 : 0) + jj * 128 + ((i - 1) >> 1) * 64, mm * 64 + (~i & 1) * 32);
          }
          __syncwarp();
          __nanosleep(PFGAP);
        }
      } else {
        if (lane < 24) {
          const uint32_t one = (lane & 8) ? 0u : 0x3F80u << ((lane & 1) * 16), w = (lane >> 1) & 3;
          sts128(sbase + OFF_ID + lane * 16, w == 0 ? one : 0u, w == 1 ? one : 0u, w == 2 ? one : 0u, w == 3 ? one : 0u);
        }
#pragma unroll 1
        for (int b = 0; b < 2; b++) {
          float4* z = reinterpret_cast<float4*>(g_kv[b] + (jj * 4) * KVH + mm * (4 * KVH / 16)) + lane;
#pragma unroll
          for (int i = 0; i < 6; i++) z[i * 32] = make_float4(0.f, 0.f, 0.f, 0.f);
        }
#pragma unroll 1
        for (int i = 0; i < 16; i++) {
          const int b = i >> 2;
          const uint32_t v = (b == 0 ? O_BIT(0) : b == 1 ? X_BIT(0) : H_BIT(0)) + 1;
          uint4* p = b < 2 ? reinterpret_cast<uint4*>(g_obuf + (size_t)(b * S_LEN + mm * 128 + (i & 3) * 32 + (lane >> 3) * 8) * D_MODEL + jj * 128 + (b ? 0 : 64)) + (lane & 7)
                           : g_halo + (size_t)(mm * 8 + jj) * 512 + i * 32 + lane;
          *p = make_uint4(v, v, v, v);
        }
        fence_proxy_async_global();
      }
      __syncwarp();
      uint32_t chkp = 0;
#pragma unroll 1
      for (int lp = hw; lp < 8 * NLAYERS; lp++) {
        const int l = lp >> 3, tk = lp & 7, ph = tk ? 2 - hw : 0;
        const uint32_t par = l & 1;
        int lane; asm volatile("mov.u32 %0, %%laneid;" : "=r"(lane));
        if (tk == 5 || (hw && tk == 0)) {
          const uint32_t bit = ph ? O_BIT(l) : X_BIT(l - 1);
          uint32_t slots = ph ? (uint32_t)(WO_ASLOT(par) >> (ph * 32 - 28)) : 0x8769876u;
          const uint32_t a0 = sbase + (lane & 7) * 126 + lane * 4 + (lane & 1) * 14;
#pragma unroll 1
          for (int c = 0; c < 7; c++, slots >>= 4) {
            const uint32_t cb = bar_chk + 112 - hw * 112 + c * 8;
#pragma unroll 1
            for (int it = 0; it < (1 << 12); it++) {
              mbar_wait_sl(cb, (chkp >> c) & 1);
              chkp ^= 1u << c;
              if (el && c == 0) PROFT(ph == 1 ? 480 + l * 2 : 488 + l * 2 + (ph >> 1));
              uint32_t bad;
              asm volatile("{\n.reg .b32 w<16>;\n"
                           "ld.shared.u32 w0, [%1 + 0];\n"
                           "ld.shared.u32 w1, [%1 + 1024];\n"
                           "ld.shared.u32 w2, [%1 + 2048];\n"
                           "ld.shared.u32 w3, [%1 + 3072];\n"
                           "ld.shared.u32 w4, [%1 + 4096];\n"
                           "ld.shared.u32 w5, [%1 + 5120];\n"
                           "ld.shared.u32 w6, [%1 + 6144];\n"
                           "ld.shared.u32 w7, [%1 + 7168];\n"
                           "ld.shared.u32 w8, [%1 + 8192];\n"
                           "ld.shared.u32 w9, [%1 + 9216];\n"
                           "ld.shared.u32 w10, [%1 + 10240];\n"
                           "ld.shared.u32 w11, [%1 + 11264];\n"
                           "ld.shared.u32 w12, [%1 + 12288];\n"
                           "ld.shared.u32 w13, [%1 + 13312];\n"
                           "ld.shared.u32 w14, [%1 + 14336];\n"
                           "ld.shared.u32 w15, [%1 + 15360];\n"
                           "lop3.b32 w0, w0, w1, %2, 0x7E;\n"
                           "lop3.b32 w2, w2, w3, %2, 0x7E;\n"
                           "lop3.b32 w4, w4, w5, %2, 0x7E;\n"
                           "lop3.b32 w6, w6, w7, %2, 0x7E;\n"
                           "lop3.b32 w8, w8, w9, %2, 0x7E;\n"
                           "lop3.b32 w10, w10, w11, %2, 0x7E;\n"
                           "lop3.b32 w12, w12, w13, %2, 0x7E;\n"
                           "lop3.b32 w14, w14, w15, %2, 0x7E;\n"
                           "lop3.b32 w0, w0, w2, w4, 0xFE;\nlop3.b32 w6, w6, w8, w10, 0xFE;\nlop3.b32 w0, w0, w12, w14, 0xFE;\nlop3.b32 %0, w0, w6, 1, 0xA8;\n}\n"
                           : "=r"(bad) : "r"(a0 + (slots & 15) * SLOT), "r"(bit) : "memory");
              if (__all_sync(0xffffffffu, bad == 0)) break;
              if (el) {
                fence_proxy_async_smem();
                mbar_expect_tx(cb, SLOT);
                tma_load_2d(sbase + (slots & 15) * SLOT, &tm_o, cb, srcb(jj, c) * 128 + (ph >> 1) * 64, mm * 128 + (ph ? 0 : S_LEN));
                RETRY_COUNT();
              }
              __syncwarp();
            }
            if (el) { mbar_arrive_local(bar_full + (c + (ph ? 25 + ph * 8 : 4)) * 8); if (lp == PRL * 8 && c == 0) PROFT(477); }
            __syncwarp();
          }
        } else if (hw && (tk & 5) == 1) {
          {
            const int hp = tk >> 1;
            const uint4* src = reinterpret_cast<const uint4*>(g_colsum[par][jj * 64 + hp * 32 + lane]);
            uint32_t bad;
            int it = 0;
            float c[6];
            do {
              bad = 0;
#pragma unroll
              for (int p = 0; p < 3; p++) {
                const uint4 v = ld_ll(src + ((par && p < 2) ? (hp ? -32 : 512) + p * 32 : p * 512));
                bad |= (v.y ^ ep1) | (v.w ^ ep1);
                c[2 * p] = __uint_as_float(v.x) + __uint_as_float(v.z); c[2 * p + 1] = __uint_as_float(v.y) + __uint_as_float(v.w);
              }
              bad &= 3;
              if (bad) __nanosleep(300);
            } while (bad && ++it < (1 << 16));
#pragma unroll
            for (int p = 0; p < 6; p++) {
              uint32_t h, m, lo;
              split3(c[p], h, m, lo);
              sts128(sbase + OFF_LNB + hp * 4096 + (p >> 1) * 1024 + lane * 32 + (p & 1) * 16, h | (m << 16), h | (lo << 16), h | (m << 16), lo | (m << 16));
            }
            fence_proxy_async_smem();
            __syncwarp();
            if (el) { mbar_arrive_local(hp ? bar_stat2 : bar_stat); if (hp == 0) PROFT(324 + l * 16); }
            __syncwarp();
          }
        } else if (tk == 0) {
          mbar_wait_sl(bar_done + 24, par);
          const uint4* sp = reinterpret_cast<const uint4*>(g_stats + (size_t)(mm * 128) * 8) + lane;
#pragma unroll 1
          for (int hf = 0; hf < 4; hf++) {
            uint4 v[4];
            uint32_t bad;
            int it = 0;
            do {
              bad = 0;
#pragma unroll
              for (int i = 0; i < 4; i++) { v[i] = ld_ll(sp + (hf * 4 + i) * 32); bad |= (v[i].y ^ STAT_TAG(l)) | (v[i].w ^ STAT_TAG(l)); }
              bad &= 3;
              if (bad) __nanosleep(200);
            } while (bad && ++it < (1 << 16));
            __syncwarp();
            float mean = 0.f, m2 = 0.f;
#pragma unroll
            for (int i = 0; i < 4; i++) {
              float a = __uint_as_float(v[i].x) + __uint_as_float(v[i].z);
              a += __shfl_xor_sync(0xffffffffu, a, 1); a += __shfl_xor_sync(0xffffffffu, a, 2);
              a *= 0.125f;
              const float e0 = __uint_as_float(v[i].x) - a, e1 = __uint_as_float(v[i].z) - a;
              float q = fmaf(fmaf(e0, e0, e1 * e1), 128.f, __uint_as_float(v[i].y) + __uint_as_float(v[i].w));
              q += __shfl_xor_sync(0xffffffffu, q, 1); q += __shfl_xor_sync(0xffffffffu, q, 2);
              if ((lane & 3) == i) { mean = a; m2 = q; }
            }
            const uint32_t row = hf * 32 + (lane & 3) * 8 + (lane >> 2);
            uint32_t h, m, lo;
            split3(-0.5f * mean, h, m, lo);
            sts128(sbase + OFF_LNA + row * 16, h | (h << 16), m | (h << 16), lo | (m << 16), m | (lo << 16));
            sts32f(sbase + OFF_ST + row * 4, rsqrtf(m2 * (1.f / 1024.f) + 1e-5f));
          }
          fence_proxy_async_smem();
          __syncwarp();
          if (el) { mbar_arrive_local(bar_stat); PROFT(323 + l * 16); }
          __syncwarp();
#pragma unroll 1
          for (int i = 0; i < 8 - 4 * l; i++) {
            asm volatile("prefetch.global.L2 [%0];" :: "l"(i < 4 ? (l ? prm.wB_o : prm.wA_o) + (size_t)cta * 8192 + i * 2048 + lane * 64
                                                                 : prm.wB_qkv + (size_t)(cta * 8 + (i - 4) * 2 + (lane >> 4)) * 3072 + 2048 + (lane & 15) * 64));
            __nanosleep(PFGAP);
          }
        } else if (lp == 3) {
#pragma unroll 1
          for (int c = 0; c < (NLAYERS > 1 ? 8 : 0); c++) {
            if (!(c & 3)) asm volatile("bar.sync %0, 288;" :: "r"(BAR_WF + (c >> 2)) : "memory");
            if (el) {
              tma_store_2d(&tm_wf, sbase + 11 * SLOT + c * 4096, (c < 4 ? 1024 : -128) + jj * 128 + (c >> 1) * 64, mm * 64 + (c & 1) * 32);
              if ((c & 3) == 3) {
                asm volatile("cp.async.bulk.commit_group;\ncp.async.bulk.wait_group.read 0;" ::: "memory");
                mbar_arrive_local(bar_phi + (c >> 2) * 8);
              } else __nanosleep(WFGAP);
            }
            __syncwarp();
          }
          if (el) { bulk_commit_wait(); signal_release(&g_flags.wfready[jj].v); PROFT(335); }
          __syncwarp();
        } else if (tk == 2 || tk == 4) {
          if (par) continue;
          const int i = tk >> 2;
          mbar_wait_sl(bar_done + (i ? HW1 : (hw ? 19 : HW0)) * 8, 0);
          const uint4* src = g_halo + (size_t)(mm * 8 + jj - 8) * 512 + i * 256 + hw * 128 + lane;
          uint4 v[4];
          int it = 0;
          bool ok;
          do {
#pragma unroll
            for (int j = 0; j < 4; j++) v[j] = mm ? ld_b128(src + j * 32) : make_uint4(H_BIT(l), 0, 0, 0);
            ok = __all_sync(0xffffffffu, (((v[0].x ^ H_BIT(l)) | (v[1].x ^ H_BIT(l)) | (v[2].x ^ H_BIT(l)) | (v[3].x ^ H_BIT(l))) & 1) == 0);
          } while (!ok && ++it < (1 << 16));
          if (lp + hw == 3 && NLAYERS > 1) mbar_wait_sl(bar_phi, 1);
#pragma unroll
          for (int j = 0; j < 4; j++) sts128(sbase + OFF_S + hw * SLOT + j * 512 + lane * 16, v[j].x, v[j].y, v[j].z, v[j].w);
          __syncwarp();
          if (el) { mbar_arrive_local(bar_halo + hw * 8); PROFT(331 + l * 16 + i * 2 + hw); }
          __syncwarp();
        } else if (tk == 6 && hw == 0 && l < NLAYERS - 1) {
          bar_sync<BAR_X1, 288>();
          if (el) {
            PROFT(328 + l * 16);
            mbar_wait_sl(bar_full + XD * 8, par ^ 1);
            tma_store_2d(&tm_o, sbase + 11 * SLOT, jj * 128 + 64, mm * 128 + S_LEN);
            bulk_commit_wait();
            signal_release(&g_flags.xready[l + 1][mm].v);
            PROFT(330 + l * 16);
          }
          __syncwarp();
        }
      }
    }
    cluster_sync();
  } else {
    asm volatile("setmaxnreg.inc.sync.aligned.u32 232;");
    const int wg = warp >> 2;
    const int r0 = warp * 16;
    const uint32_t pK = sbase + OFF_S, pV = sbase + OFF_S + SLOT;
#define PMASKS(on, bit) const uint32_t pm0 = ((on) && t == (g >> 1)), pbit = (bit)
#define PBIT(w) (((w) & ~pm0) | (pbit & pm0))
#define LANE_CONSTS() \
    int lane; asm volatile("mov.u32 %0, %%laneid;" : "=r"(lane)); \
    const int g = lane >> 2, t = lane & 3; \
    const uint32_t srowoff = (r0 + (lane & 15)) * 128, lsw = (lane & 7) << 4, lhi = (lane >> 4) << 4, lsw2 = (lane & 6) << 3; \
    (void)g; (void)t; (void)srowoff; (void)lsw; (void)lhi; (void)lsw2;
    uint32_t stgp = 0, peer;
    asm volatile("mapa.shared::cluster.u32 %0, %1, %2;" : "=r"(peer) : "r"(sbase), "r"(rank ^ 1));
    peer -= sbase;
    const uint32_t dA0 = (((sbase & 0x3FFFF) + wg * 8192) >> 4) | 0x10000u, dB0 = ((sbase & 0x3FFFF) >> 4) | 0x2000000u;
    cluster_wait();
#define DESC(lo, hi) ((uint64_t)(uint32_t)(lo) | ((uint64_t)(hi) << 32))
#define STG_ARRIVE() { __syncwarp(); if (elect_one()) mbar_arrive_local(bar_stg); }
#define STG_WAIT() { mbar_wait(bar_stg, stgp); stgp ^= 1; }
#define PROFS() do {} while (0)
#define REL(addr) { if (elect_one()) { mbar_arrive_local(addr); asm volatile("mbarrier.arrive.shared::cluster.b64 _, [%0];" :: "r"((addr) + peer) : "memory"); } }
#define QSTEP(ACC, DA, SC) { \
      const uint32_t da = (DA), db = dB0 + (ub & 0x18) * (QST >> 7); \
      mbar_wait(ub, par); \
      wgmma_fence(); \
      wgmma4_n192<SC>(ACC, da, db); \
      wgmma_commit(); PROFS(); }
#define QREL() { wgmma_wait<1>(); REL(ub + 376); ub += 8; }
#define RA_CUR (dA0 + (OFF_RA >> 4) + (ub & 0x18) * (SLOT >> 7))
#define PUMP1() { QSTEP(S1, RA_CUR, 1); QREL(); }
#define PUMP0() { PUMP1(); SCHED_FENCE(); }
#define PUMP() if (h == 0) PUMP1()
#define WSTEP() { \
      const uint32_t s4 = (ub - bar_full - 256) >> 1; \
      const uint32_t da = dA0 + (((uint32_t)(WO_ASLOT(par) >> s4) & 15) << 10), db = dB0 + (((uint32_t)(WO_BSLOT >> s4) & 15) << 10); \
      mbar_wait(ub, par); \
      wgmma_fence(); \
      wgmma4_n128<1>(S1, da, db); \
      wgmma_commit(); PROFS(); \
      wgmma_wait<1>(); \
      if (s4) REL(ub + 376); \
      ub += 8; }
#define PUMPS(n) { _Pragma("unroll 1") for (int i_ = 0; i_ < (n); i_++) PUMP1(); }
#define LNSTEP(ACC, hh) { wgmma_fence(); wgmma_n192<1, 0>(ACC, make_desc(sbase + OFF_LNA + wg * 1024, 0, 128) ^ (1ull << 62), make_desc(sbase + OFF_LNB + (hh) * 4096, 0, 128) ^ (1ull << 62)); }
#define WARP_STORE(tm, tile, col, row) { fence_proxy_async_smem(); __syncwarp(); \
      if (elect_one()) { tma_store_2d(tm, (tile) + r0 * 128, col, (row) + r0); asm volatile("cp.async.bulk.commit_group;" ::: "memory"); } __syncwarp(); }
#define TILE_CONSTS(base, on, bit) \
      uint32_t ta[5]; \
      { PMASKS(on, bit); (void)pbit; ta[4] = pm0; } \
      _Pragma("unroll") for (int j = 0; j < 4; j++) ta[j] = (base) + srowoff + ((((uint32_t)j << 5) + lhi) ^ lsw); \
      PINU(ta, 5); SCHED_FENCE(); \
      const uint32_t pm0 = ta[4], pbit = (bit)
#define X_OUT(pc, W) { \
      _Pragma("unroll") for (int j = 0; j < 4; j++) \
        stsm_x4(ta[j] + (pc) * SLOT, \
                PBIT(pack_bf16((W)[j * 8 + 0], (W)[j * 8 + 1])), PBIT(pack_bf16((W)[j * 8 + 2], (W)[j * 8 + 3])), \
                (pack_bf16((W)[j * 8 + 4], (W)[j * 8 + 5])), (pack_bf16((W)[j * 8 + 6], (W)[j * 8 + 7]))); }
#define REST_P1(SKEW) { \
      mbar_wait(bar_stat2, par); \
      LNSTEP(S1, 1); \
      _Pragma("unroll 1") while (ub < bar_full + 256) { \
        if (ub == bar_full + 256 - 8 * (SKEW) && wg == 0) bar_sync<BAR_SKEW, 256>(); \
        QSTEP(S1, RA_CUR, 1); \
        if (ub == bar_full + 248 && wg == 1) bar_arrive<BAR_SKEW, 256>(); \
        QREL(); \
      } \
      mbar_wait(bar_done + (31 - (SKEW)) * 8, par);        \
      wgmma_wait<0>(); \
      ACC_FENCE(S1, 96); \
      REL(bar_done + 31 * 8); \
      PROF(13); }
#define FOLD(tile, rd) { \
          LANE_CONSTS(); \
          float d[32]; \
          ACC_DEF(d, 32); \
          mbar_wait(bar_phi, 0); \
          wgmma_fence(); \
          _Pragma("unroll") for (int i = 0; i < 2; i++) { \
            const uint64_t da = make_desc((tile) + wg * 8192 + i * 64, 16, 1024); \
            const uint64_t db = make_desc(sbase + OFF_PHI + wg * 4096 + i * 2048, 16, 512) ^ (3ull << 62); \
            wgmma_n32<0>(d + i * 16, da, db); wgmma_n32<1>(d + i * 16, da + 2, db + 64); \
          } \
          wgmma_commit(); \
          PUMP0(); \
          ACC_FENCE(d, 32); \
          bar_wg(wg); \
          _Pragma("unroll") for (int i = 0; i < 4; i++) { \
            const float* x = d + (i & 1) * 8 + (i >> 1) * 2; \
            if (rd) sts128((tile) + wg * 8192 + ((warp & 3) * 16 + (i >> 1) * 8 + g) * 128 + (((2 * t + (i & 1)) ^ g) << 4), \
                           pack_bf16(x[0], x[1]), pack_bf16(x[4], x[5]), pack_bf16(x[16], x[17]), pack_bf16(x[20], x[21])); \
            else stsm_x4((tile) + srowoff + ((((uint32_t)i << 5) + lhi) ^ lsw), pack_bf16(d[i * 8], d[i * 8 + 1]), pack_bf16(d[i * 8 + 2], d[i * 8 + 3]), \
                         pack_bf16(d[i * 8 + 4], d[i * 8 + 5]), pack_bf16(d[i * 8 + 6], d[i * 8 + 7])); \
          } \
          }
#define XM_ISSUE() { mbar_wait(bar_xr, par); wgmma_fence(); \
      wgmma_copy(T_, dA0 + (OFF_RA >> 4), make_desc(sbase + OFF_ID, 128, 128) ^ (1ull << 62)); }
#define COPYN(d, s, n) _Pragma("unroll") for (int i_ = 0; i_ < (n); i_++) { uint32_t c_; asm volatile("mov.b32 %0, %1;" : "=r"(c_) : "f"((s)[i_])); (d)[i_] = __uint_as_float(c_); }
#define COPY64(d, s) COPYN(d, s, 64)
#define XM_DONE() { ACC_FENCE(T_, 64); COPY64(S1, T_); ACC_FENCE(S1, 64); \
      __syncwarp(); if (elect_one()) mbar_arrive_local(bar_lx); }
#define LOAD_X() { float T_[64]; ACC_DEF(T_, 64); wgmma_wait<0>(); XM_ISSUE(); wgmma_commit(); wgmma_wait<0>(); XM_DONE(); }

    float S0[96], S1[96];
#define FIRST_STEP(l_) { const int ln_ = (l_), l = ln_; const uint32_t ub = bar_full; (void)l; (void)ub; ACC_DEF(S0, 96); wgmma_fence(); wgmma4_n192<0>(S0, dA0 + (OFF_S >> 4), dB0); wgmma_commit(); PROFS(); }
    mbar_wait(bar_full, 0);
    FIRST_STEP(0);
    LOAD_EPOCH();
#pragma unroll 1
    for (int l = 0;; l++) {
      const uint32_t par = l & 1;
      uint32_t ub = bar_full + 8;
      PROF(1);
      {
        LANE_CONSTS();
        uint32_t ta[4];
#pragma unroll
        for (int j = 0; j < 4; j++) ta[j] = pK + srowoff + ((((uint32_t)j << 5) + lhi) ^ lsw);
        float p0, p1, a0 = 0.f, a1 = 0.f, q0 = 0.f, q1 = 0.f;
#define STATS(j0, j1) _Pragma("unroll") for (int j = (j0); j < (j1); j++) { \
          uint32_t x[4]; \
          ldsm_x4(ta[j & 3] + (j >> 2) * SLOT, x[0], x[1], x[2], x[3]); \
          if (j == 0) { p0 = __shfl_sync(0xffffffffu, bf_lo(x[0]), lane & 28); p1 = __shfl_sync(0xffffffffu, bf_lo(x[1]), lane & 28); } \
          _Pragma("unroll") for (int i = 0; i < 4; i += 2) { \
            const float d0 = bf_lo(x[i]) - p0, d1 = bf_hi(x[i]) - p0, d2 = bf_lo(x[i + 1]) - p1, d3 = bf_hi(x[i + 1]) - p1; \
            a0 += d0 + d1; a1 += d2 + d3; \
            q0 = fmaf(d1, d1, fmaf(d0, d0, q0)); q1 = fmaf(d3, d3, fmaf(d2, d2, q1)); } } \
          asm volatile("" : "+f"(a0), "+f"(a1), "+f"(q0), "+f"(q1), "+f"(p0), "+f"(p1)); SCHED_FENCE()
        if (SB0) { STATS(0, SB0); }
        bar_wg(wg);
        QSTEP(S0, dA0 + ((OFF_S + SLOT) >> 4), 1);
        QREL();
        SCHED_FENCE();
        STATS(SB0, SB1);
        ACC_DEF(S1, 96);
        QSTEP(S1, dA0 + (OFF_S >> 4), 0);
        QREL();
        SCHED_FENCE();
        STATS(SB1, SB2);
        QSTEP(S1, dA0 + ((OFF_S + SLOT) >> 4), 1);
        QREL();
        SCHED_FENCE();
        STATS(SB2, 8);
#pragma unroll
        for (int o = 1; o <= 2; o <<= 1) {
          a0 += __shfl_xor_sync(0xffffffffu, a0, o); a1 += __shfl_xor_sync(0xffffffffu, a1, o);
          q0 += __shfl_xor_sync(0xffffffffu, q0, o); q1 += __shfl_xor_sync(0xffffffffu, q1, o);
        }
        if (t == 1) { a0 = a1; q0 = q1; p0 = p1; }
        if (t < 2) st_b64(g_stats + (size_t)(mm * 128 + r0 + g + t * 8) * 8 + jj, __float_as_uint(fmaf(a0, 1.f / 128.f, p0)),
                          (__float_as_uint(fmaxf(fmaf(a0 * (-1.f / 128.f), a0, q0), 0.f)) & ~3u) | STAT_TAG(l));
        if (l) { asm volatile("cp.async.bulk.wait_group 0;" ::: "memory"); bar_arrive<BAR_X1, 288>(); }
#pragma unroll 1
        for (int i = 0; i < 14; i++) {
          QSTEP(S0, RA_CUR, 1);
          if (i == 0) PROF(2);
          QREL();
        }
      }
      LANE_CONSTS();
      mbar_wait(bar_stat, par);
      LNSTEP(S0, 0);
      wgmma_commit();
      const float rs0 = lds32f(sbase + OFF_ST + (r0 + g) * 4), rs1 = lds32f(sbase + OFF_ST + (r0 + g + 8) * 4);
      PUMP0();
      ACC_FENCE(S0, 96);
      PROF(3);
      if (!par) {
        constexpr uint32_t par = 0;
        uint32_t qa[16];
        uint32_t kf[32], vf[32];
#define DRAIN_A(ACC, hp, PMP) { \
          LANE_CONSTS(); \
          FRAG(kf + 16, ACC + 32, 0, (hp) * 2); \
          PMP; \
          FRAG(vf + 16, ACC + 64, 1, (hp) * 2 + 1); \
          _Pragma("unroll") for (int i_ = 0; i_ < 16; i_++) qa[i_] = pack_bf16(ACC[2 * i_], ACC[2 * i_ + 1]); \
          PINU(qa, 16); }
        DRAIN_A(S0, 0, PUMP0());
        if (l == 0 && NLAYERS > 1) {
#pragma unroll 1
          for (int rd = 1; rd >= 0; rd--) {
            FOLD(sbase + (12 - rd) * SLOT, rd);
            fence_proxy_async_smem();
            asm volatile("bar.arrive %0, 288;" :: "r"(BAR_WF + 1 - rd) : "memory");
          }
        }
        PUMPS(FPUMP);
        if (l == 0 && NLAYERS > 1) mbar_wait(bar_phi, 1);
#pragma unroll 1
        for (int h = 0; h < 2; h++) {
          PROFH(4, 16);
          LANE_CONSTS();
          FRAG_PUT(kf + 16, 10); FRAG_PUT(vf + 16, 11);
          STG_ARRIVE();
          if (h) { PROF(8); LOAD_X(); PROF(9); WSTEP(); PROF(10); } else PUMPS(HPUMP2);
          const bool e = g & 1, hb = (2 * t + (g & 1)) <= g;
          uint32_t sel[3] = {e ? 0x1044u : 0x4410u, hb ? 0x4444u : (e ? 0x3244u : 0x4432u), hb ? (e ? 0x3244u : 0x4432u) : 0x4444u};
          PINU(sel, 3);
          TILE_CONSTS(sbase, true, O_BIT(l));
          const uint32_t selA = sel[0], selL = sel[1], selH = sel[2];
          if (h) PROF(12);
          STG_WAIT();
          if (h) PROF(14);
          if (warp == 0) mbar_wait(bar_halo, h);
          if (h) PROF(15);
          FRAG_GET(kf, 10);
          PROFH(5, 17);
          float s[2][4][4];
#pragma unroll
          for (int ks = 0; ks < 2; ks++)
#pragma unroll
            for (int i = 0; i < 8; i++) {
              const int hh = (i >> 1) & 1, jb = (i & 1) + (~i >> 1 & 2);
              const uint32_t* b = kf + (jb >> 1) * 16 + hh * 8 + ks * 4 + (jb & 1) * 2;
              if (ks) mma_bf16(s[hh][jb], qa[hh * 8 + 4], qa[hh * 8 + 5], qa[hh * 8 + 6], qa[hh * 8 + 7], b[0], b[1]);
              else mma_bf16_z(s[hh][jb], qa[hh * 8], qa[hh * 8 + 1], qa[hh * 8 + 2], qa[hh * 8 + 3], b[0], b[1]);
            }
          PUMP();
          PROFH(6, 18);
          float va[2][2], vb[2][2], mx[2][2];
#pragma unroll
          for (int hh = 0; hh < 2; hh++) {
            va[hh][0] = e ? s[hh][1][1] : s[hh][1][0];
            vb[hh][0] = hb ? (e ? s[hh][2][1] : s[hh][2][0]) : (e ? s[hh][0][1] : s[hh][0][0]);
            va[hh][1] = e ? s[hh][2][3] : s[hh][2][2];
            vb[hh][1] = hb ? (e ? s[hh][3][3] : s[hh][3][2]) : (e ? s[hh][1][3] : s[hh][1][2]);
          }
          if (warp == 0 && mm == 0) {
#pragma unroll
            for (int hh = 0; hh < 2; hh++) { va[hh][0] = -INFINITY; if (!hb) { vb[hh][0] = -INFINITY; vb[hh][1] = -INFINITY; } }
          }
#pragma unroll
          for (int i = 0; i < 4; i++) mx[i >> 1][i & 1] = fmaxf(va[i >> 1][i & 1], vb[i >> 1][i & 1]);
#pragma unroll
          for (int o = 1; o <= 2; o <<= 1)
#pragma unroll
            for (int i = 0; i < 4; i++) mx[i >> 1][i & 1] = fmaxf(mx[i >> 1][i & 1], __shfl_xor_sync(0xffffffffu, mx[i >> 1][i & 1], o));
          const float sc0 = rs0 * (0.17677669529663687f * LOG2E), sc1 = rs1 * (0.17677669529663687f * LOG2E);
#pragma unroll
          for (int i = 0; i < 4; i++) {
            const float sc = (i & 1) ? sc1 : sc0, m = mx[i >> 1][i & 1];
            va[i >> 1][i & 1] = ex2((va[i >> 1][i & 1] - m) * sc); vb[i >> 1][i & 1] = ex2((vb[i >> 1][i & 1] - m) * sc);
            mx[i >> 1][i & 1] = va[i >> 1][i & 1] + vb[i >> 1][i & 1];
          }
          if (h == 0) { PIN(&va[0][0], 4); PIN(&vb[0][0], 4); PIN(&mx[0][0], 4); PUMP1(); }
          if (h) PROF(20);
          if (warp == 0) mbar_wait(bar_halo + 8, h);
          if (h) PROF(21);
          FRAG_GET(vf, 11);
#pragma unroll
          for (int o = 1; o <= 2; o <<= 1)
#pragma unroll
            for (int i = 0; i < 4; i++) mx[i >> 1][i & 1] += __shfl_xor_sync(0xffffffffu, mx[i >> 1][i & 1], o);
          float o[2][4][4];
          uint32_t pa[2][8];
#pragma unroll
          for (int hh = 0; hh < 2; hh++) {
            const float i0 = rcp_fast(mx[hh][0]), i1 = rcp_fast(mx[hh][1]);
            const uint32_t w0 = pack_bf16(va[hh][0] * i0, vb[hh][0] * i0), w1 = pack_bf16(va[hh][1] * i1, vb[hh][1] * i1);
            pa[hh][0] = __byte_perm(w0, 0, selL); pa[hh][2] = __byte_perm(w0, 0, selA); pa[hh][3] = __byte_perm(w1, 0, selL);
            pa[hh][4] = __byte_perm(w0, 0, selH); pa[hh][5] = __byte_perm(w1, 0, selA); pa[hh][7] = __byte_perm(w1, 0, selH);
            pa[hh][1] = pa[hh][0] & pa[hh][4]; pa[hh][6] = pa[hh][3] & pa[hh][7];
          }
          PROFH(7, 19);
#pragma unroll
          for (int i = 0; i < 8; i++) mma_bf16_z(o[i >> 2][i & 3], pa[i >> 2][4], pa[i >> 2][5], pa[i >> 2][6], pa[i >> 2][7], vf[16 + 2 * i], vf[17 + 2 * i]);
#pragma unroll
          for (int i = 0; i < 8; i++) mma_bf16(o[i >> 2][i & 3], pa[i >> 2][0], pa[i >> 2][1], pa[i >> 2][2], pa[i >> 2][3], vf[2 * i], vf[2 * i + 1]);
          if (h == 0) PUMP1() else mbar_wait(bar_done + 30 * 8, par);
          if (NLAYERS > 1) mbar_wait(bar_phi + 8, 0);
          if (h) PROF(22);
#pragma unroll
          for (int i = 0; i < 4; i++) {
            const int hh = i >> 1, dp = i & 1;
            stsm_x4(ta[i] + (h ? 3 : 12) * SLOT,
                    PBIT(pack_bf16(o[hh][dp * 2][0], o[hh][dp * 2][1])), PBIT(pack_bf16(o[hh][dp * 2][2], o[hh][dp * 2][3])),
                    pack_bf16(o[hh][dp * 2 + 1][0], o[hh][dp * 2 + 1][1]), pack_bf16(o[hh][dp * 2 + 1][2], o[hh][dp * 2 + 1][3]));
          }
          WARP_STORE(&tm_os, sbase + (h ? 3 : 12) * SLOT, jj * 128 + h * 64, mm * 128);
          PROFH(11, 23);
          if (h) break;
          REST_P1(ASKEW);
          asm volatile("cp.async.bulk.wait_group.read 0;" ::: "memory");
          DRAIN_A(S1, 1, {});
        }
      } else {
        constexpr uint32_t par = 1;
        float st[32];
        const float c0 = rs0 * LOG2E, c1 = rs1 * LOG2E;
        { V_ADDR(pV, 0); STAGE_V(S0 + 64); }
        if (warp < 2) sts128(sbase + OFF_ONES + warp * 512 + lane * 16, 0x3F803F80u, 0x3F803F80u, 0x3F803F80u, 0x3F803F80u);
        scale32(st, S0, c0, c1);
        PIN(st, 32);
#define PHI_PIECE(c) { \
          e_[2 * (c)] = ex2(st[2 * (c)]); e_[2 * (c) + 1] = ex2(st[2 * (c) + 1]); \
          _Pragma("unroll") for (int k_ = 4 * (c); k_ < 4 * (c) + 4; k_++) m_[(c) >> 1] = (k_ & 7) ? fmaf(st[k_], st[k_], m_[(c) >> 1]) : st[k_] * st[k_]; \
          asm volatile("" : "+f"(e_[2 * (c)]), "+f"(e_[2 * (c) + 1]), "+f"(m_[(c) >> 1])); SCHED_FENCE(); }
#define PHI_FIN() { \
          big = __any_sync(0xffffffffu, !(fmaxf(fmaxf(m_[0], m_[1]), fmaxf(m_[2], m_[3])) < BIGLIM)); \
          if (__builtin_expect(big, 0)) { COPYN(e_, st, 16); } \
          _Pragma("unroll") for (int k_ = 0; k_ < 16; k_++) st[k_] = e_[k_]; \
          PIN(st, 16); }
#define KV_MMA(vs, IL) { \
          const uint32_t dp = dA0 + 12 * 1024 - wg * 2560, dv = dA0 + (vs) * 1024 + ((OFF_ONES - (vs) * SLOT - 16) << 12) - wg * (512 << 16); \
          STG_WAIT(); \
          wgmma_fence(); \
          _Pragma("unroll") for (int ks = 0; ks < 8; ks++) { \
            const uint64_t a = DESC(dp + ks * 128, 0x40000040), b = DESC(dv + ks * (64 - (64 << 16)), 0x80000020); \
            if ((IL) && ks) wgmma_fence(); \
            if (ks == 0) wgmma_n40<0, 1>(kv, a, b); else wgmma_n40<1, 1>(kv, a, b); \
            if (ks == 7) wgmma_commit(); \
            if (IL) PHI_PIECE(ks); } }
#define KV_RED1(i) if (h) red_v4(g_kv[l >> 1] + (jj * 4) * KVH + warp * 768 + lane * 4 + (i) * 128, S0[32 + (i) * 3], S0[33 + (i) * 3], S0[34 + (i) * 3], 1.f)
#define KV_REDS(n) { _Pragma("unroll") for (int i_ = 0; i_ < 6; i_++) if (((RPACE >> (4 * i_)) & 15) == (n)) KV_RED1(i_); }
#define KV_SEND(kp) { \
          float sd[9]; \
          _Pragma("unroll") for (int i = 0; i < 8; i++) { (kp)[i] = kv[i]; sd[i] = kv[8 + i]; } \
          (kp)[8] = rank ? kv[18] : kv[16]; sd[8] = rank ? kv[16] : kv[18]; \
          const uint32_t ra = sbase + peer + (warp * 32 + lane) * 4, rb = bar_kx + peer; \
          if (elect_one()) mbar_expect_tx(bar_kx, 1152); \
          _Pragma("unroll") for (int i = 0; i < 2; i++) \
            asm volatile("st.async.weak.shared::cluster.mbarrier::complete_tx::bytes.v4.f32 [%0], {%1, %2, %3, %4}, [%5];" \
                         :: "r"(ra + (warp * 32 + lane) * 12 + OFF_PHI + i * 4096), "f"(sd[4 * i]), "f"(sd[4 * i + 1]), "f"(sd[4 * i + 2]), "f"(sd[4 * i + 3]), "r"(rb) : "memory"); \
          asm volatile("st.async.weak.shared::cluster.mbarrier::complete_tx::bytes.f32 [%0], %1, [%2];" :: "r"(ra + OFF_LNB), "f"(sd[8]), "r"(rb) : "memory"); }
#define KV_RECV(kp, hp) { \
          float r_[9]; \
          float* kvg = g_kv[l >> 1] + (jj * 4 + (hp) * 2) * KVH + warp * 768 + rank * 384 + lane * 4; \
          mbar_wait(bar_kx, l >> 1); \
          _Pragma("unroll") for (int i = 0; i < 2; i++) \
            asm volatile("ld.shared.v4.f32 {%0, %1, %2, %3}, [%4];" : "=f"(r_[4 * i]), "=f"(r_[4 * i + 1]), "=f"(r_[4 * i + 2]), "=f"(r_[4 * i + 3]) \
                         : "r"(sbase + OFF_PHI + i * 4096 + (warp * 32 + lane) * 16) : "memory"); \
          r_[8] = lds32f(sbase + OFF_LNB + (warp * 32 + lane) * 4); \
          _Pragma("unroll") for (int i = 0; i < 3; i++) red_v4(kvg + i * 128, (kp)[3 * i] + r_[3 * i], (kp)[3 * i + 1] + r_[3 * i + 1], (kp)[3 * i + 2] + r_[3 * i + 2], 2.f); }
#define KV_LOAD(hp) { \
          const uint4* kvg = reinterpret_cast<const uint4*>(g_kv[l >> 1] + (jj * 4 + (hp) * 2) * KVH) + warp * 192 + lane; \
          _Pragma("unroll") for (int i = 0; i < 6; i++) v[i] = ld_b128(kvg + i * 32); }
#define KVV(i) __uint_as_float((i) % 3 == 0 ? v[(i) / 3].x : ((i) % 3 == 1 ? v[(i) / 3].y : v[(i) / 3].z))
#define KV_TILE(hp) { \
          _Pragma("unroll 1") for (int it = 0; it < (1 << 16); it++) { \
            if (__all_sync(0xffffffffu, (v[0].w & v[1].w & v[2].w & v[3].w & v[4].w & v[5].w) == 0x41800000u)) break; \
            RETRY_COUNT(); \
            KV_LOAD(hp); \
          } \
          if (hp) PROF(26); else PROF(25); \
          const uint32_t e = lane & 7, jt = ((lane >> 1) & 4) + (e >> 1); \
          const uint32_t row = ((((warp >> 1) ^ wg) & 1) << 5) + ((jt & 1) << 4) + ((warp & 1) << 3) + (jt & 6) + (e & 1); \
          const uint32_t kd = pV + wg * 8192 + row * 128, ksw = (row & 7) << 4; \
          _Pragma("unroll") for (int i = 0; i < 2; i++) \
            stsm_x4(kd + ((i * 32 + lhi) ^ ksw), pack_bf16(KVV(i * 9), KVV(i * 9 + 1)), pack_bf16(KVV(i * 9 + 2), KVV(i * 9 + 3)), \
                    pack_bf16(KVV(i * 9 + 4), KVV(i * 9 + 5)), pack_bf16(KVV(i * 9 + 6), KVV(i * 9 + 7))); \
          stsm_x4(kd + ((64u + lhi) ^ ksw), pack_bf16(KVV(8), 1.f), pack_bf16(KVV(17), 1.f), 0u, 0u); }
#pragma unroll 1
        for (int h = 0; h < 2; h++) {
          PROFH(4, 6);
          PUMP0();
          LANE_CONSTS();
          const uint32_t dsw = (uint32_t)(g ^ (2 * t)) << 4, dst = ((t & 2) ? pK : sbase + 12 * SLOT) + (r0 + g) * 128;
          float e[16], f[16];
          KV_REDS(1);
          float sa = exps16_<0>(e, st);
          exps16_fix<0>(e, st, sa);
          asm volatile("" : "+f"(sa)); PIN(e, 16); PUMP0();
          if (h) STG_WAIT();
          KV_REDS(2);
          store16(e, sa, dst, dsw, 4);
          float sb = exps16_<1>(f, st);
          exps16_fix<1>(f, st, sb);
          asm volatile("" : "+f"(sb)); PIN(f, 16); PUMP0();
          KV_REDS(3);
          store16(f, sb, dst, dsw, 0);
          float sc = exps16_<0>(e, st + 2);
          exps16_fix<0>(e, st + 2, sc);
          asm volatile("" : "+f"(sc)); PIN(e, 16); PUMP0();
          KV_REDS(4);
          store16(e, sc, dst + 1024, dsw, 4);
          float sd = exps16_<1>(f, st + 2);
          exps16_fix<1>(f, st + 2, sd);
          asm volatile("" : "+f"(sd)); PIN(f, 16); PUMP0();
          store16(f, sd, dst + 1024, dsw, 0);
          PROFH(5, 7);
          if (h) break;
          {
            float kv[20];
            ACC_DEF(kv, 20);
            fence_proxy_async_smem();
            STG_ARRIVE();
            float e_[16], m_[4];
            KV_MMA(11, 0);
            PUMP0();
            ACC_FENCE(kv, 20);
            STG_ARRIVE();
            scale32(st, S0 + 32, c0, c1);
            PIN(st, 32);
            {
              COPYN(S0 + 32, kv, 8); COPYN(S0 + 40, kv + 16, 1); COPYN(S0 + 41, kv + 8, 8); COPYN(S0 + 49, kv + 18, 1);
              const int h = 1;
              KV_REDS(0);
            }
          }
        }
        bool big;
        uint4 v[6];
        {
          float kv[20];
          { LANE_CONSTS(); KV_LOAD(0); }
          mbar_wait(bar_stat2, par);
          LNSTEP(S1, 1);
          ub = bar_full + 240;
          PUMP1();
          if (wg == 0) bar_sync<BAR_SKEW, 256>();
          QSTEP(S1, RA_CUR, 1);
          if (wg == 1) bar_arrive<BAR_SKEW, 256>();
          QREL();
          { LANE_CONSTS(); KV_TILE(0); }
          LANE_CONSTS();
          V_ADDR(sbase + 3 * SLOT, rank * 32);
          PINU(va_, 2);
          mbar_wait(bar_done + 30 * 8, par);
          wgmma_wait<0>();
          ACC_FENCE(S1, 96);
          PROF(13);
          STAGE_V(S1 + 64);
          fence_proxy_async_smem();
          STG_ARRIVE();
          REL(bar_done + 31 * 8);
          scale32(st, S1, c0, c1);
          PIN(st, 32);
          PROF(16);
          ACC_DEF(kv, 20);
          float e_[16], m_[4];
          KV_MMA(3, 1);
          SCHED_FENCE();
          PROF(14);
          PHI_FIN();
          SCHED_FENCE();
          PROF(15);
          wgmma_wait<0>();
          ACC_FENCE(kv, 20);
          PROF(12);
          { float kp[9]; KV_SEND(kp); _Pragma("unroll") for (int i = 0; i < 3; i++) v[i] = make_uint4(__float_as_uint(kp[3 * i]), __float_as_uint(kp[3 * i + 1]), __float_as_uint(kp[3 * i + 2]), 0u); }
          PROF(17);
        }
#pragma unroll 1
        for (int h = 0; h < 2; h++) {
          const uint32_t pO = sbase + (h ? 3 : 8) * SLOT;
          LANE_CONSTS();
          uint32_t fq[32];
          PROFH(18, 32);
          SCHED_FENCE();
          phiq_b<1>(fq, st, big); PINU(fq, 16); PIN(st + 16, 16);
          SCHED_FENCE();
          PROFH(8, 9);
          if (h) {
            asm volatile("cp.async.bulk.wait_group.read 0;" ::: "memory");
            mbar_wait(bar_lx, par);
            PROF(30);
            KV_TILE(1);
            fence_proxy_async_smem();
            STG_ARRIVE();
          }
          SCHED_FENCE();
          if (h == 0) {
            float kp[9];
#pragma unroll
            for (int i = 0; i < 9; i++) kp[i] = KVV(i);
            KV_RECV(kp, 1);
            SCHED_FENCE();
          }
          phiq_b<0>(fq + 16, st + 16, big); PINU(fq + 16, 16);
          PROFH(10, 21);
          if (h) STG_WAIT();
          wgmma_wait<0>();
          ACC_FENCE(S1, 64);
          PROFH(19, 33);
          float o[4][20];
#define O_MMA(hh) { \
            const uint64_t db = make_desc(pV + (hh) * 8192, 16, 1024); \
            ACC_DEF(o[(hh) * 2], 20); ACC_DEF(o[(hh) * 2 + 1], 20); \
            wgmma_fence(); \
            wgmma_n40_rs<0>(o[(hh) * 2], fq + (hh) * 16, db + 256); wgmma_n40_rs<0>(o[(hh) * 2 + 1], fq + (hh) * 16 + 8, db); \
            wgmma_n40_rs<1>(o[(hh) * 2], fq + (hh) * 16 + 4, db + 384); wgmma_n40_rs<1>(o[(hh) * 2 + 1], fq + (hh) * 16 + 12, db + 128); \
            wgmma_commit(); }
          O_MMA(0);
          SCHED_FENCE();
          PMASKS(true, O_BIT(l));
#pragma unroll
          for (int hh = 0; hh < 2; hh++) {
            wgmma_wait<0>();
            ACC_FENCE(o[hh * 2], 20); ACC_FENCE(o[hh * 2 + 1], 20);
            if (!hh) { O_MMA(1); SCHED_FENCE(); }
            if (hh) PROFH(22, 24);
            const float* x = o[hh * 2];
            const float* y = o[hh * 2 + 1];
            const float sx0 = x[17] * 0x1p-40f, sy0 = y[17] * 0x1p-40f, sx1 = x[19] * 0x1p-40f, sy1 = y[19] * 0x1p-40f;
            const float i0 = rcp_fast(fmaf(fmaf(x[17], 1e-6f, x[16]), sy0, y[16] * sx0)), i1 = rcp_fast(fmaf(fmaf(x[19], 1e-6f, x[18]), sy1, y[18] * sx1));
            const float ax0 = sy0 * i0, ay0 = sx0 * i0, ax1 = sy1 * i1, ay1 = sx1 * i1;
#pragma unroll
            for (int dp = 0; dp < 2; dp++)
              stsm_x4(pO + srowoff + ((hh * 64 + dp * 32 + lhi) ^ lsw),
                      PBIT(pack_bf16(fmaf(x[dp * 8], ax0, y[dp * 8] * ay0), fmaf(x[dp * 8 + 1], ax0, y[dp * 8 + 1] * ay0))),
                      PBIT(pack_bf16(fmaf(x[dp * 8 + 2], ax1, y[dp * 8 + 2] * ay1), fmaf(x[dp * 8 + 3], ax1, y[dp * 8 + 3] * ay1))),
                      (pack_bf16(fmaf(x[dp * 8 + 4], ax0, y[dp * 8 + 4] * ay0), fmaf(x[dp * 8 + 5], ax0, y[dp * 8 + 5] * ay0))),
                      (pack_bf16(fmaf(x[dp * 8 + 6], ax1, y[dp * 8 + 6] * ay1), fmaf(x[dp * 8 + 7], ax1, y[dp * 8 + 7] * ay1))));
          }
          WARP_STORE(&tm_os, pO, jj * 128 + h * 64, mm * 128);
          PROFH(20, 34);
          if (h) break;
          float T_[64];
          scale32(st, S1 + 32, c0, c1);
          PIN(st, 32);
          ACC_DEF(T_, 64);
          XM_ISSUE(); wgmma_commit();
          SCHED_FENCE();
          big = any_big(st);
          SCHED_FENCE();
          PROF(27);
          wgmma_wait<0>(); XM_DONE();
          PROF(28);
          bar_wg(wg);
          WSTEP();
          SCHED_FENCE();
          PROF(29);
          KV_LOAD(1);
          phiq_a(st, big); PIN(st, 16);
          PROF(31);
        }
      }
      __syncwarp();
      if (elect_one()) mbar_arrive_local(bar_epi);
      bar_wg(wg);
#pragma unroll 1
      while (ub < bar_full + 384) {
        WSTEP();
        if (ub == bar_full + 8 * 41) { asm volatile("cp.async.bulk.wait_group.read 0;" ::: "memory"); PROF(35); }
        if (ub == bar_full + 8 * 42) PROF(36);
      }
      {
        float Wb[32];
        LANE_CONSTS();
        TILE_CONSTS(pK, l < NLAYERS - 1, X_BIT(l));
        if (l < NLAYERS - 1) mbar_wait(bar_full, par ^ 1);
        wgmma_wait<0>();
        ACC_FENCE(S1, 64);
        COPYN(Wb, S1 + 32, 32);
        PROF(37);
        X_OUT(0, S1);
        WARP_STORE(l < NLAYERS - 1 ? &tm_os : &tm_xo, pK, jj * 128, mm * 128 + (l < NLAYERS - 1 ? S_LEN : 0));
        if (l == NLAYERS - 1) { PMASKS(false, 0); X_OUT(1, Wb); break; }
        PROF(38);
        bar_wg(wg);
        FIRST_STEP(l + 1);
        REL(bar_done + 47 * 8);
        PROF(39);
        { PMASKS(false, 0); X_OUT(1, Wb); }
        fence_proxy_async_smem();
      }
    }
    WARP_STORE(&tm_xo, pV, jj * 128 + 64, mm * 128);
    asm volatile("cp.async.bulk.wait_group.read 0;" ::: "memory");
    cluster_sync();
  }
}

typedef CUresult (*PFN_encode)(CUtensorMap*, CUtensorMapDataType, cuuint32_t, void*, const cuuint64_t*, const cuuint64_t*,
                               const cuuint32_t*, const cuuint32_t*, CUtensorMapInterleave, CUtensorMapSwizzle,
                               CUtensorMapL2promotion, CUtensorMapFloatOOBfill);

CUtensorMap make_map(PFN_encode enc, const void* ptr, uint64_t inner, uint64_t outer, uint32_t box_inner, uint32_t box_outer,
                     CUtensorMapSwizzle swz = CU_TENSOR_MAP_SWIZZLE_128B, int promo = CU_TENSOR_MAP_L2_PROMOTION_L2_256B) {
  CUtensorMap m;
  cuuint64_t dims[2] = {inner, outer};
  cuuint64_t strides[1] = {inner * 2};
  cuuint32_t box[2] = {box_inner, box_outer};
  cuuint32_t es[2] = {1, 1};
  enc(&m, CU_TENSOR_MAP_DATA_TYPE_BFLOAT16, 2, const_cast<void*>(ptr), dims, strides, box, es, CU_TENSOR_MAP_INTERLEAVE_NONE,
      swz, (CUtensorMapL2promotion)promo, CU_TENSOR_MAP_FLOAT_OOB_FILL_NONE);
  return m;
}

}

extern "C" void kernel_launch(void* const* d_in, const int* in_sizes, int n_in, void* d_out, int out_size) {
  (void)in_sizes; (void)n_in; (void)out_size;
  static PFN_encode enc = nullptr;
  if (!enc) {
    void* fn = nullptr;
    cudaDriverEntryPointQueryResult qr;
    cudaGetDriverEntryPoint("cuTensorMapEncodeTiled", &fn, cudaEnableDefault, &qr);
    enc = (PFN_encode)fn;
    cudaFuncSetAttribute(mega_kernel, cudaFuncAttributeMaxDynamicSharedMemorySize, SMEM_BYTES);
  }
  Params prm;
  prm.x0 = (const __nv_bfloat16*)d_in[0];
  prm.wA_qkv = (const __nv_bfloat16*)d_in[1];
  prm.wA_o = (const __nv_bfloat16*)d_in[2];
  prm.wB_qkv = (const __nv_bfloat16*)d_in[4];
  prm.wB_phi = (const __nv_bfloat16*)d_in[5];
  prm.wB_o = (const __nv_bfloat16*)d_in[6];
  prm.out = (__nv_bfloat16*)d_out;
  void *obuf = nullptr, *wf = nullptr;
  cudaGetSymbolAddress(&obuf, g_obuf);
  cudaGetSymbolAddress(&wf, g_wfold);
  CUtensorMap tm_x0 = make_map(enc, d_in[0], D_MODEL, S_LEN, 64, 128, CU_TENSOR_MAP_SWIZZLE_128B, XPROMO);
  CUtensorMap tm_xo = make_map(enc, d_out, D_MODEL, S_LEN, 64, 16);
  CUtensorMap tm_os = make_map(enc, obuf, D_MODEL, 2 * S_LEN, 64, 16);
  CUtensorMap tm_o = make_map(enc, obuf, D_MODEL, 2 * S_LEN, 64, 128, CU_TENSOR_MAP_SWIZZLE_128B, OPROMO);
  CUtensorMap tm_wf = make_map(enc, wf, 2048, D_MODEL, 64, 32);
  CUtensorMap tm_wqA = make_map(enc, d_in[1], 3 * D_MODEL, D_MODEL, 64, 32, CU_TENSOR_MAP_SWIZZLE_128B, WPROMO);
  CUtensorMap tm_wqB = make_map(enc, prm.wB_qkv, 3 * D_MODEL, D_MODEL, 64, 32);
  CUtensorMap tm_woA = make_map(enc, prm.wA_o, D_MODEL, D_MODEL, 64, 64);
  CUtensorMap tm_woB = make_map(enc, prm.wB_o, D_MODEL, D_MODEL, 64, 64);
  CUtensorMap tm_phi = make_map(enc, prm.wB_phi, 32, 1024, 32, 128, CU_TENSOR_MAP_SWIZZLE_64B);
  mega_kernel<<<NMAIN + NAUX, 384, SMEM_BYTES>>>(tm_x0, tm_xo, tm_os, tm_o, tm_wf, tm_wqA, tm_wqB, tm_woA, tm_woB, tm_phi, prm);
}
```

```cpp
#include <cuda_runtime.h>
#include <cuda.h>
#include <cuda_bf16.h>
#include <stdint.h>

#define NLAYERS 4

#define HPUMP2 1
#define ASKEW 2
#define FPUMP 3
#define PFGAP 100
#define POLLGAP 120
#define HW1 29
#define XPACE 0x06050401000000ull
#define XP0 4
#define HW0 18
#define XD 4
#define WFGAP 50
#define EARLY 2
#define BIGLIM 3600.f
#define SUMLO 0x1p-100f
#define SUMHI 0x1p100f
#define XPROMO 2
#define OPROMO 3
#define STAG2 300
#define WPROMO 3
#define SB0 2
#define SB1 4
#define SB2 6
#define PROWS 3
#define SPD0 0
#define SPD1 0
#define SPD2 300
#define FRB 0x3535353535ull
#define NOB 0xFFFFFF00u
#define NO1 ~0u
#define NOX ~0u
#define FD0 0
#define FD1 3
#define RPACE 0x221100
namespace {

constexpr int S_LEN = 2048, D_MODEL = 1024;
constexpr int NAUX = 4, NMAIN = 128;
constexpr int SLOT = 16384;
constexpr int QST = 24576;
constexpr int OFF_RA = 6 * SLOT, OFF_S = 10 * SLOT;
constexpr int OFF_HALO = 13 * SLOT, OFF_LNB = OFF_HALO  , OFF_ONES = OFF_HALO + 3072;
constexpr int OFF_ST = OFF_HALO + 7168  , OFF_ID = OFF_HALO + 7680, OFF_PHI = OFF_HALO + 8192;
constexpr int OFF_BAR = 14 * SLOT;
constexpr int OFF_LNA = OFF_BAR + 1024;
constexpr int SMEM_BYTES = OFF_LNA + 2048;
#define WO_ASLOT(par) ((par) ? 0x9876CAB39876CA98ull : 0x98C76BA398C7698Cull)
constexpr unsigned long long WO_BSLOT = 0x5432105421054210ull;
__device__ __forceinline__ int srcb(int j, int i) { return (i + (i >= j)) & 7; }
__device__ __forceinline__ int kslice(int j, int i) { return i < 2 ? 2 * j + i : (i < 9 ? 2 * srcb(j, i - 2) : 2 * srcb(j, i - 9) + 1); }
__device__ __forceinline__ int wslice(int j, int s) { return 2 * ((s & 7) ? srcb(j, (s & 7) - 1) : j) + (s >> 3); }
constexpr int KVH = 6 * 128 * 4;

struct __align__(128) Flag { unsigned v; unsigned pad[31]; };
struct Flags {
  Flag xready[4][16];
  Flag wfready[8];
  Flag done;
  Flag epoch;
};

__device__ Flags g_flags;
__device__ __nv_bfloat16 g_obuf[2 * S_LEN * D_MODEL];
#define O_BIT(l) ((epoch * NLAYERS + (l) + 1) & 1u)
#define X_BIT(l) ((epoch * (NLAYERS - 1) + (l) + 1) & 1u)
__device__ __nv_bfloat16 g_wfold[D_MODEL * 2048];
__device__ uint4 g_halo[16 * 8 * 512];
__device__ __align__(128) float g_kv[2][32 * KVH];
__device__ __align__(128) uint2 g_colsum[2][1536][2];
__device__ __align__(128) uint2 g_stats[S_LEN * 8];
#define H_BIT(l) (NLAYERS > 2 ? (uint32_t)((l) == 0) : (ep1 & 1))
#define STAT_TAG(l) ((ep1 * NLAYERS + (l) + 1) & 3u)

#define RETRY_COUNT()
#define PRL 0
#define PRU 0
#define PROFL 1
#define PROFW 0
#define PROFT(i) do {} while (0)
#define PROF(i) do {} while (0)
#define PROFH(i, j) do {} while (0)

__device__ __forceinline__ uint32_t smem_u32(const void* p) { return (uint32_t)__cvta_generic_to_shared(p); }
__device__ __forceinline__ bool elect_one() {
  uint32_t p;
  asm volatile("{\n.reg .pred p;\nelect.sync _|p, 0xffffffff;\nselp.u32 %0, 1, 0, p;\n}\n" : "=r"(p));
  return p != 0;
}
__device__ __forceinline__ void mbar_init(uint32_t bar, uint32_t cnt) {
  asm volatile("mbarrier.init.shared::cta.b64 [%0], %1;" :: "r"(bar), "r"(cnt));
}
__device__ __forceinline__ void mbar_expect_tx(uint32_t bar, uint32_t bytes) {
  asm volatile("mbarrier.arrive.expect_tx.shared::cta.b64 _, [%0], %1;" :: "r"(bar), "r"(bytes) : "memory");
}
#define mbar_wait(bar, parity) \
  asm volatile("{\n.reg .pred p, q;\nW_%=:\nmbarrier.try_wait.parity.shared::cta.b64 p, [%1], %2;\nadd.s32 %0, %0, -1;\n" \
               "setp.gt.and.s32 q, %0, 0, !p;\n@q bra.uni W_%=;\n}\n" : "+r"(budget) : "r"((uint32_t)(bar)), "r"((uint32_t)(parity)) : "memory")
#define mbar_wait_sl(bar, parity) \
  asm volatile("{\n.reg .pred p, q;\nW_%=:\nmbarrier.try_wait.parity.shared::cta.b64 p, [%1], %2, 20000;\nadd.s32 %0, %0, -64;\n" \
               "setp.gt.and.s32 q, %0, 0, !p;\n@q bra.uni W_%=;\n}\n" : "+r"(budget) : "r"((uint32_t)(bar)), "r"((uint32_t)(parity)) : "memory")
__device__ __forceinline__ void mbar_arrive_local(uint32_t bar) {
  asm volatile("mbarrier.arrive.shared::cta.b64 _, [%0];" :: "r"(bar) : "memory");
}
__device__ __forceinline__ void tma_load_2d(uint32_t dst, const CUtensorMap* tm, uint32_t bar, int c0, int c1) {
  asm volatile("cp.async.bulk.tensor.2d.shared::cluster.global.mbarrier::complete_tx::bytes [%0], [%1, {%3, %4}], [%2];"
               :: "r"(dst), "l"(tm), "r"(bar), "r"(c0), "r"(c1) : "memory");
}
__device__ __forceinline__ void tma_load_2d_mc(uint32_t dst, const CUtensorMap* tm, uint32_t bar, int c0, int c1) {
  asm volatile("cp.async.bulk.tensor.2d.shared::cluster.global.mbarrier::complete_tx::bytes.multicast::cluster [%0], [%1, {%3, %4}], [%2], %5;"
               :: "r"(dst), "l"(tm), "r"(bar), "r"(c0), "r"(c1), "h"((uint16_t)3) : "memory");
}
__device__ __forceinline__ void tma_store_2d(const CUtensorMap* tm, uint32_t src, int c0, int c1) {
  asm volatile("cp.async.bulk.tensor.2d.global.shared::cta.bulk_group [%0, {%2, %3}], [%1];"
               :: "l"(tm), "r"(src), "r"(c0), "r"(c1) : "memory");
}
__device__ __forceinline__ void tma_load_t(uint32_t dst, const CUtensorMap* tm, uint32_t bar, int c0, int row) {
  asm volatile("cp.async.bulk.tensor.4d.shared::cluster.global.mbarrier::complete_tx::bytes [%0], [%1, {%3, %5, %5, %4}], [%2];"
               :: "r"(dst), "l"(tm), "r"(bar), "r"(c0), "r"(row >> 5), "r"(0) : "memory");
}
__device__ __forceinline__ void tma_store_t(const CUtensorMap* tm, uint32_t src, int c0, int row) {
  asm volatile("cp.async.bulk.tensor.4d.global.shared::cta.bulk_group [%0, {%2, %4, %4, %3}], [%1];"
               :: "l"(tm), "r"(src), "r"(c0), "r"(row >> 5), "r"(0) : "memory");
}
__device__ __forceinline__ void bulk_commit_wait() {
  asm volatile("cp.async.bulk.commit_group;\ncp.async.bulk.wait_group 0;" ::: "memory");
}
__device__ __forceinline__ void prefetch_tmap(const CUtensorMap* tm) {
  asm volatile("prefetch.tensormap [%0];" :: "l"(tm) : "memory");
}
__device__ __forceinline__ void fence_proxy_async_global() { asm volatile("fence.proxy.async.global;" ::: "memory"); }
__device__ __forceinline__ void fence_proxy_async_smem() { asm volatile("fence.proxy.async.shared::cta;" ::: "memory"); }
__device__ __forceinline__ unsigned ld_relaxed(const unsigned* p) {
  unsigned v;
  asm volatile("ld.relaxed.gpu.global.u32 %0, [%1];" : "=r"(v) : "l"(p) : "memory");
  return v;
}
__device__ __forceinline__ void fence_acquire() { asm volatile("fence.acquire.gpu;" ::: "memory"); }
__device__ __forceinline__ void wait_flag(const unsigned* p, unsigned target) {
  int it = 0;
  while ((int)(ld_relaxed(p) - target) < 0 && ++it < (1 << 20)) {}
  fence_acquire();
}
__device__ __forceinline__ void signal_release(unsigned* p) {
  asm volatile("red.release.gpu.global.add.u32 [%0], 1;" :: "l"(p) : "memory");
}
template <int ID, int N> __device__ __forceinline__ void bar_arrive() { asm volatile("bar.arrive %0, %1;" :: "n"(ID), "n"(N) : "memory"); }
template <int ID, int N> __device__ __forceinline__ void bar_sync() { asm volatile("bar.sync %0, %1;" :: "n"(ID), "n"(N) : "memory"); }
__device__ __forceinline__ void bar_wg(int wg) { asm volatile("bar.sync %0, 128;" :: "r"(2 + wg) : "memory"); }
__device__ __forceinline__ void cluster_sync() {
  asm volatile("barrier.cluster.arrive.relaxed.aligned;\nbarrier.cluster.wait.aligned;" ::: "memory");
}
__device__ __forceinline__ void cluster_wait() { asm volatile("barrier.cluster.wait.acquire.aligned;" ::: "memory"); }
enum { BAR_X1 = 7, BAR_WF = 8  , BAR_SKEW = 10 };

__device__ __forceinline__ void wgmma_fence() { asm volatile("wgmma.fence.sync.aligned;" ::: "memory"); }
__device__ __forceinline__ void wgmma_commit() { asm volatile("wgmma.commit_group.sync.aligned;" ::: "memory"); }
template <int N> __device__ __forceinline__ void wgmma_wait() { asm volatile("wgmma.wait_group.sync.aligned %0;" :: "n"(N) : "memory"); }

template <int scale_d, int tnsp_b = 1> __device__ __forceinline__ void wgmma_n192(float* d, uint64_t descA, uint64_t descB) {
  asm volatile("{\n.reg .pred p;\nsetp.ne.b32 p, %98, 0;\n"
               "wgmma.mma_async.sync.aligned.m64n192k16.f32.bf16.bf16 {%0,%1,%2,%3,%4,%5,%6,%7,%8,%9,%10,%11,%12,%13,%14,%15,%16,%17,%18,%19,%20,%21,%22,%23,%24,%25,%26,%27,%28,%29,%30,%31,%32,%33,%34,%35,%36,%37,%38,%39,%40,%41,%42,%43,%44,%45,%46,%47,%48,%49,%50,%51,%52,%53,%54,%55,%56,%57,%58,%59,%60,%61,%62,%63,%64,%65,%66,%67,%68,%69,%70,%71,%72,%73,%74,%75,%76,%77,%78,%79,%80,%81,%82,%83,%84,%85,%86,%87,%88,%89,%90,%91,%92,%93,%94,%95}, %96, %97, p, 1, 1, 0, %99;\n}\n"
               : "+f"(d[0]), "+f"(d[1]), "+f"(d[2]), "+f"(d[3]), "+f"(d[4]), "+f"(d[5]), "+f"(d[6]), "+f"(d[7]), "+f"(d[8]), "+f"(d[9]), "+f"(d[10]), "+f"(d[11]), "+f"(d[12]), "+f"(d[13]), "+f"(d[14]), "+f"(d[15]), "+f"(d[16]), "+f"(d[17]), "+f"(d[18]), "+f"(d[19]), "+f"(d[20]), "+f"(d[21]), "+f"(d[22]), "+f"(d[23]), "+f"(d[24]), "+f"(d[25]), "+f"(d[26]), "+f"(d[27]), "+f"(d[28]), "+f"(d[29]), "+f"(d[30]), "+f"(d[31]), "+f"(d[32]), "+f"(d[33]), "+f"(d[34]), "+f"(d[35]), "+f"(d[36]), "+f"(d[37]), "+f"(d[38]), "+f"(d[39]), "+f"(d[40]), "+f"(d[41]), "+f"(d[42]), "+f"(d[43]), "+f"(d[44]), "+f"(d[45]), "+f"(d[46]), "+f"(d[47]), "+f"(d[48]), "+f"(d[49]), "+f"(d[50]), "+f"(d[51]), "+f"(d[52]), "+f"(d[53]), "+f"(d[54]), "+f"(d[55]), "+f"(d[56]), "+f"(d[57]), "+f"(d[58]), "+f"(d[59]), "+f"(d[60]), "+f"(d[61]), "+f"(d[62]), "+f"(d[63]), "+f"(d[64]), "+f"(d[65]), "+f"(d[66]), "+f"(d[67]), "+f"(d[68]), "+f"(d[69]), "+f"(d[70]), "+f"(d[71]), "+f"(d[72]), "+f"(d[73]), "+f"(d[74]), "+f"(d[75]), "+f"(d[76]), "+f"(d[77]), "+f"(d[78]), "+f"(d[79]), "+f"(d[80]), "+f"(d[81]), "+f"(d[82]), "+f"(d[83]), "+f"(d[84]), "+f"(d[85]), "+f"(d[86]), "+f"(d[87]), "+f"(d[88]), "+f"(d[89]), "+f"(d[90]), "+f"(d[91]), "+f"(d[92]), "+f"(d[93]), "+f"(d[94]), "+f"(d[95])
               : "l"(descA), "l"(descB), "n"(scale_d), "n"(tnsp_b));
}
template <int scale_d> __device__ __forceinline__ void wgmma4_n192(float* d, uint32_t da, uint32_t db) {
#define R_ "{%0,%1,%2,%3,%4,%5,%6,%7,%8,%9,%10,%11,%12,%13,%14,%15,%16,%17,%18,%19,%20,%21,%22,%23,%24,%25,%26,%27,%28,%29,%30,%31,%32,%33,%34,%35,%36,%37,%38,%39,%40,%41,%42,%43,%44,%45,%46,%47,%48,%49,%50,%51,%52,%53,%54,%55,%56,%57,%58,%59,%60,%61,%62,%63,%64,%65,%66,%67,%68,%69,%70,%71,%72,%73,%74,%75,%76,%77,%78,%79,%80,%81,%82,%83,%84,%85,%86,%87,%88,%89,%90,%91,%92,%93,%94,%95}"
  asm volatile("{\n.reg .pred p, q;\n.reg .b64 a, b;\nsetp.ne.b32 p, %98, 0;\nsetp.eq.b32 q, 0, 0;\nmov.b64 a, {%96, 0x40000040};\nmov.b64 b, {%97, 0x40000040};\n"
               "wgmma.mma_async.sync.aligned.m64n192k16.f32.bf16.bf16 " R_ ", a, b, p, 1, 1, 0, 1;\nadd.s64 a, a, 2;\nadd.s64 b, b, 128;\n"
               "wgmma.mma_async.sync.aligned.m64n192k16.f32.bf16.bf16 " R_ ", a, b, q, 1, 1, 0, 1;\nadd.s64 a, a, 2;\nadd.s64 b, b, 128;\n"
               "wgmma.mma_async.sync.aligned.m64n192k16.f32.bf16.bf16 " R_ ", a, b, q, 1, 1, 0, 1;\nadd.s64 a, a, 2;\nadd.s64 b, b, 128;\n"
               "wgmma.mma_async.sync.aligned.m64n192k16.f32.bf16.bf16 " R_ ", a, b, q, 1, 1, 0, 1;\n}\n"
               : "+f"(d[0]), "+f"(d[1]), "+f"(d[2]), "+f"(d[3]), "+f"(d[4]), "+f"(d[5]), "+f"(d[6]), "+f"(d[7]), "+f"(d[8]), "+f"(d[9]), "+f"(d[10]), "+f"(d[11]), "+f"(d[12]), "+f"(d[13]), "+f"(d[14]), "+f"(d[15]), "+f"(d[16]), "+f"(d[17]), "+f"(d[18]), "+f"(d[19]), "+f"(d[20]), "+f"(d[21]), "+f"(d[22]), "+f"(d[23]), "+f"(d[24]), "+f"(d[25]), "+f"(d[26]), "+f"(d[27]), "+f"(d[28]), "+f"(d[29]), "+f"(d[30]), "+f"(d[31]), "+f"(d[32]), "+f"(d[33]), "+f"(d[34]), "+f"(d[35]), "+f"(d[36]), "+f"(d[37]), "+f"(d[38]), "+f"(d[39]), "+f"(d[40]), "+f"(d[41]), "+f"(d[42]), "+f"(d[43]), "+f"(d[44]), "+f"(d[45]), "+f"(d[46]), "+f"(d[47]), "+f"(d[48]), "+f"(d[49]), "+f"(d[50]), "+f"(d[51]), "+f"(d[52]), "+f"(d[53]), "+f"(d[54]), "+f"(d[55]), "+f"(d[56]), "+f"(d[57]), "+f"(d[58]), "+f"(d[59]), "+f"(d[60]), "+f"(d[61]), "+f"(d[62]), "+f"(d[63]), "+f"(d[64]), "+f"(d[65]), "+f"(d[66]), "+f"(d[67]), "+f"(d[68]), "+f"(d[69]), "+f"(d[70]), "+f"(d[71]), "+f"(d[72]), "+f"(d[73]), "+f"(d[74]), "+f"(d[75]), "+f"(d[76]), "+f"(d[77]), "+f"(d[78]), "+f"(d[79]), "+f"(d[80]), "+f"(d[81]), "+f"(d[82]), "+f"(d[83]), "+f"(d[84]), "+f"(d[85]), "+f"(d[86]), "+f"(d[87]), "+f"(d[88]), "+f"(d[89]), "+f"(d[90]), "+f"(d[91]), "+f"(d[92]), "+f"(d[93]), "+f"(d[94]), "+f"(d[95])
               : "r"(da), "r"(db), "n"(scale_d));
#undef R_
}
template <int scale_d> __device__ __forceinline__ void wgmma4_n128(float* d, uint32_t da, uint32_t db) {
#define R_ "{%0,%1,%2,%3,%4,%5,%6,%7,%8,%9,%10,%11,%12,%13,%14,%15,%16,%17,%18,%19,%20,%21,%22,%23,%24,%25,%26,%27,%28,%29,%30,%31,%32,%33,%34,%35,%36,%37,%38,%39,%40,%41,%42,%43,%44,%45,%46,%47,%48,%49,%50,%51,%52,%53,%54,%55,%56,%57,%58,%59,%60,%61,%62,%63}"
  asm volatile("{\n.reg .pred p, q;\n.reg .b64 a, b;\nsetp.ne.b32 p, %66, 0;\nsetp.eq.b32 q, 0, 0;\nmov.b64 a, {%64, 0x40000040};\nmov.b64 b, {%65, 0x40000040};\n"
               "wgmma.mma_async.sync.aligned.m64n128k16.f32.bf16.bf16 " R_ ", a, b, p, 1, 1, 0, 1;\nadd.s64 a, a, 2;\nadd.s64 b, b, 128;\n"
               "wgmma.mma_async.sync.aligned.m64n128k16.f32.bf16.bf16 " R_ ", a, b, q, 1, 1, 0, 1;\nadd.s64 a, a, 2;\nadd.s64 b, b, 128;\n"
               "wgmma.mma_async.sync.aligned.m64n128k16.f32.bf16.bf16 " R_ ", a, b, q, 1, 1, 0, 1;\nadd.s64 a, a, 2;\nadd.s64 b, b, 128;\n"
               "wgmma.mma_async.sync.aligned.m64n128k16.f32.bf16.bf16 " R_ ", a, b, q, 1, 1, 0, 1;\n}\n"
               : "+f"(d[0]), "+f"(d[1]), "+f"(d[2]), "+f"(d[3]), "+f"(d[4]), "+f"(d[5]), "+f"(d[6]), "+f"(d[7]), "+f"(d[8]), "+f"(d[9]), "+f"(d[10]), "+f"(d[11]), "+f"(d[12]), "+f"(d[13]), "+f"(d[14]), "+f"(d[15]), "+f"(d[16]), "+f"(d[17]), "+f"(d[18]), "+f"(d[19]), "+f"(d[20]), "+f"(d[21]), "+f"(d[22]), "+f"(d[23]), "+f"(d[24]), "+f"(d[25]), "+f"(d[26]), "+f"(d[27]), "+f"(d[28]), "+f"(d[29]), "+f"(d[30]), "+f"(d[31]), "+f"(d[32]), "+f"(d[33]), "+f"(d[34]), "+f"(d[35]), "+f"(d[36]), "+f"(d[37]), "+f"(d[38]), "+f"(d[39]), "+f"(d[40]), "+f"(d[41]), "+f"(d[42]), "+f"(d[43]), "+f"(d[44]), "+f"(d[45]), "+f"(d[46]), "+f"(d[47]), "+f"(d[48]), "+f"(d[49]), "+f"(d[50]), "+f"(d[51]), "+f"(d[52]), "+f"(d[53]), "+f"(d[54]), "+f"(d[55]), "+f"(d[56]), "+f"(d[57]), "+f"(d[58]), "+f"(d[59]), "+f"(d[60]), "+f"(d[61]), "+f"(d[62]), "+f"(d[63])
               : "r"(da), "r"(db), "n"(scale_d));
#undef R_
}
template <int scale_d> __device__ __forceinline__ void wgmma_n32(float* d, uint64_t descA, uint64_t descB) {
  asm volatile("{\n.reg .pred p;\nsetp.ne.b32 p, %18, 0;\n"
               "wgmma.mma_async.sync.aligned.m64n32k16.f32.bf16.bf16 {%0,%1,%2,%3,%4,%5,%6,%7,%8,%9,%10,%11,%12,%13,%14,%15}, %16, %17, p, 1, 1, 0, 1;\n}\n"
               : "+f"(d[0]), "+f"(d[1]), "+f"(d[2]), "+f"(d[3]), "+f"(d[4]), "+f"(d[5]), "+f"(d[6]), "+f"(d[7]), "+f"(d[8]), "+f"(d[9]), "+f"(d[10]), "+f"(d[11]), "+f"(d[12]), "+f"(d[13]), "+f"(d[14]), "+f"(d[15])
               : "l"(descA), "l"(descB), "n"(scale_d));
}
template <int scale_d, int tnsp_a> __device__ __forceinline__ void wgmma_n40(float* d, uint64_t descA, uint64_t descB) {
  asm volatile("{\n.reg .pred p;\nsetp.ne.b32 p, %22, 0;\n"
               "wgmma.mma_async.sync.aligned.m64n40k16.f32.bf16.bf16 {%0,%1,%2,%3,%4,%5,%6,%7,%8,%9,%10,%11,%12,%13,%14,%15,%16,%17,%18,%19}, %20, %21, p, 1, 1, %23, 1;\n}\n"
               : "+f"(d[0]), "+f"(d[1]), "+f"(d[2]), "+f"(d[3]), "+f"(d[4]), "+f"(d[5]), "+f"(d[6]), "+f"(d[7]), "+f"(d[8]), "+f"(d[9]), "+f"(d[10]), "+f"(d[11]), "+f"(d[12]), "+f"(d[13]), "+f"(d[14]), "+f"(d[15]), "+f"(d[16]), "+f"(d[17]), "+f"(d[18]), "+f"(d[19])
               : "l"(descA), "l"(descB), "n"(scale_d), "n"(tnsp_a));
}
template <int scale_d> __device__ __forceinline__ void wgmma_n40_rs(float* d, const uint32_t* a, uint64_t descB) {
  asm volatile("{\n.reg .pred p;\nsetp.ne.b32 p, %25, 0;\n"
               "wgmma.mma_async.sync.aligned.m64n40k16.f32.bf16.bf16 {%0,%1,%2,%3,%4,%5,%6,%7,%8,%9,%10,%11,%12,%13,%14,%15,%16,%17,%18,%19}, {%20,%21,%22,%23}, %24, p, 1, 1, 1;\n}\n"
               : "+f"(d[0]), "+f"(d[1]), "+f"(d[2]), "+f"(d[3]), "+f"(d[4]), "+f"(d[5]), "+f"(d[6]), "+f"(d[7]), "+f"(d[8]), "+f"(d[9]), "+f"(d[10]), "+f"(d[11]), "+f"(d[12]), "+f"(d[13]), "+f"(d[14]), "+f"(d[15]), "+f"(d[16]), "+f"(d[17]), "+f"(d[18]), "+f"(d[19])
               : "r"(a[0]), "r"(a[1]), "r"(a[2]), "r"(a[3]), "l"(descB), "n"(scale_d));
}
__device__ __forceinline__ void wgmma_copy(float* d, uint32_t da, uint64_t descB) {
  asm volatile("{\n.reg .pred p;\n.reg .b64 a;\nsetp.ne.b32 p, 0, 0;\nmov.b64 a, {%64, 0x40000040};\n"
               "wgmma.mma_async.sync.aligned.m64n16k16.f32.bf16.bf16 {%0,%1,%2,%3,%4,%5,%6,%7}, a, %65, p, 1, 1, 0, 0;\nadd.s64 a, a, 2;\n"
               "wgmma.mma_async.sync.aligned.m64n16k16.f32.bf16.bf16 {%8,%9,%10,%11,%12,%13,%14,%15}, a, %65, p, 1, 1, 0, 0;\nadd.s64 a, a, 2;\n"
               "wgmma.mma_async.sync.aligned.m64n16k16.f32.bf16.bf16 {%16,%17,%18,%19,%20,%21,%22,%23}, a, %65, p, 1, 1, 0, 0;\nadd.s64 a, a, 2;\n"
               "wgmma.mma_async.sync.aligned.m64n16k16.f32.bf16.bf16 {%24,%25,%26,%27,%28,%29,%30,%31}, a, %65, p, 1, 1, 0, 0;\nadd.s64 a, a, 1018;\n"
               "wgmma.mma_async.sync.aligned.m64n16k16.f32.bf16.bf16 {%32,%33,%34,%35,%36,%37,%38,%39}, a, %65, p, 1, 1, 0, 0;\nadd.s64 a, a, 2;\n"
               "wgmma.mma_async.sync.aligned.m64n16k16.f32.bf16.bf16 {%40,%41,%42,%43,%44,%45,%46,%47}, a, %65, p, 1, 1, 0, 0;\nadd.s64 a, a, 2;\n"
               "wgmma.mma_async.sync.aligned.m64n16k16.f32.bf16.bf16 {%48,%49,%50,%51,%52,%53,%54,%55}, a, %65, p, 1, 1, 0, 0;\nadd.s64 a, a, 2;\n"
               "wgmma.mma_async.sync.aligned.m64n16k16.f32.bf16.bf16 {%56,%57,%58,%59,%60,%61,%62,%63}, a, %65, p, 1, 1, 0, 0;\n"
               "}\n"
               : "+f"(d[0]), "+f"(d[1]), "+f"(d[2]), "+f"(d[3]), "+f"(d[4]), "+f"(d[5]), "+f"(d[6]), "+f"(d[7]), "+f"(d[8]), "+f"(d[9]), "+f"(d[10]), "+f"(d[11]), "+f"(d[12]), "+f"(d[13]), "+f"(d[14]), "+f"(d[15]), "+f"(d[16]), "+f"(d[17]), "+f"(d[18]), "+f"(d[19]), "+f"(d[20]), "+f"(d[21]), "+f"(d[22]), "+f"(d[23]), "+f"(d[24]), "+f"(d[25]), "+f"(d[26]), "+f"(d[27]), "+f"(d[28]), "+f"(d[29]), "+f"(d[30]), "+f"(d[31]), "+f"(d[32]), "+f"(d[33]), "+f"(d[34]), "+f"(d[35]), "+f"(d[36]), "+f"(d[37]), "+f"(d[38]), "+f"(d[39]), "+f"(d[40]), "+f"(d[41]), "+f"(d[42]), "+f"(d[43]), "+f"(d[44]), "+f"(d[45]), "+f"(d[46]), "+f"(d[47]), "+f"(d[48]), "+f"(d[49]), "+f"(d[50]), "+f"(d[51]), "+f"(d[52]), "+f"(d[53]), "+f"(d[54]), "+f"(d[55]), "+f"(d[56]), "+f"(d[57]), "+f"(d[58]), "+f"(d[59]), "+f"(d[60]), "+f"(d[61]), "+f"(d[62]), "+f"(d[63])
               : "r"(da), "l"(descB));
}
__device__ __forceinline__ uint64_t make_desc(uint32_t addr, uint32_t lbo_bytes, uint32_t sbo_bytes) {
  return (uint64_t)((addr & 0x3FFFF) >> 4) | ((uint64_t)(lbo_bytes >> 4) << 16) | ((uint64_t)(sbo_bytes >> 4) << 32) | (1ull << 62);
}

__device__ __forceinline__ void ldsm_x4(uint32_t addr, uint32_t& r0, uint32_t& r1, uint32_t& r2, uint32_t& r3) {
  asm volatile("ldmatrix.sync.aligned.m8n8.x4.shared.b16 {%0,%1,%2,%3}, [%4];" : "=r"(r0), "=r"(r1), "=r"(r2), "=r"(r3) : "r"(addr) : "memory");
}
__device__ __forceinline__ void ldsm_x4_t(uint32_t addr, uint32_t& r0, uint32_t& r1, uint32_t& r2, uint32_t& r3) {
  asm volatile("ldmatrix.sync.aligned.m8n8.x4.trans.shared.b16 {%0,%1,%2,%3}, [%4];" : "=r"(r0), "=r"(r1), "=r"(r2), "=r"(r3) : "r"(addr) : "memory");
}
__device__ __forceinline__ void stsm_x4(uint32_t addr, uint32_t r0, uint32_t r1, uint32_t r2, uint32_t r3) {
  asm volatile("stmatrix.sync.aligned.m8n8.x4.shared.b16 [%0], {%1,%2,%3,%4};" :: "r"(addr), "r"(r0), "r"(r1), "r"(r2), "r"(r3) : "memory");
}
__device__ __forceinline__ void stsm_x4_t(uint32_t addr, uint32_t r0, uint32_t r1, uint32_t r2, uint32_t r3) {
  asm volatile("stmatrix.sync.aligned.m8n8.x4.trans.shared.b16 [%0], {%1,%2,%3,%4};" :: "r"(addr), "r"(r0), "r"(r1), "r"(r2), "r"(r3) : "memory");
}
__device__ __forceinline__ void sts128(uint32_t addr, uint32_t a, uint32_t b, uint32_t c, uint32_t d) {
  asm volatile("st.shared.v4.u32 [%0], {%1,%2,%3,%4};" :: "r"(addr), "r"(a), "r"(b), "r"(c), "r"(d) : "memory");
}
__device__ __forceinline__ float lds32f(uint32_t addr) {
  float v;
  asm volatile("ld.shared.f32 %0, [%1];" : "=f"(v) : "r"(addr) : "memory");
  return v;
}
__device__ __forceinline__ void sts32f(uint32_t addr, float a) {
  asm volatile("st.shared.f32 [%0], %1;" :: "r"(addr), "f"(a) : "memory");
}
__device__ __forceinline__ void mma_bf16(float (&c)[4], uint32_t a0, uint32_t a1, uint32_t a2, uint32_t a3, uint32_t b0, uint32_t b1) {
  asm volatile("mma.sync.aligned.m16n8k16.row.col.f32.bf16.bf16.f32 {%0,%1,%2,%3}, {%4,%5,%6,%7}, {%8,%9}, {%0,%1,%2,%3};"
               : "+f"(c[0]), "+f"(c[1]), "+f"(c[2]), "+f"(c[3]) : "r"(a0), "r"(a1), "r"(a2), "r"(a3), "r"(b0), "r"(b1));
}
__device__ __forceinline__ void mma_bf16_z(float (&c)[4], uint32_t a0, uint32_t a1, uint32_t a2, uint32_t a3, uint32_t b0, uint32_t b1) {
  asm volatile("mma.sync.aligned.m16n8k16.row.col.f32.bf16.bf16.f32 {%0,%1,%2,%3}, {%4,%5,%6,%7}, {%8,%9}, {%10,%10,%10,%10};"
               : "=f"(c[0]), "=f"(c[1]), "=f"(c[2]), "=f"(c[3]) : "r"(a0), "r"(a1), "r"(a2), "r"(a3), "r"(b0), "r"(b1), "f"(0.f));
}
__device__ __forceinline__ uint32_t movm_t(uint32_t v) {
  uint32_t r;
  asm volatile("movmatrix.sync.aligned.m8n8.trans.b16 %0, %1;" : "=r"(r) : "r"(v));
  return r;
}
__device__ __forceinline__ uint32_t pack_bf16(float lo, float hi) {
  uint32_t r;
  asm("cvt.rn.bf16x2.f32 %0, %1, %2;" : "=r"(r) : "f"(hi), "f"(lo));
  return r;
}
__device__ __forceinline__ float bf_lo(uint32_t v) { return __uint_as_float(v << 16); }
__device__ __forceinline__ float bf_hi(uint32_t v) { return __uint_as_float(v & 0xFFFF0000u); }
__device__ __forceinline__ void split3(float x, uint32_t& h, uint32_t& m, uint32_t& l) {
  h = pack_bf16(x, 0.f); x -= bf_lo(h);
  m = pack_bf16(x, 0.f); x -= bf_lo(m);
  l = pack_bf16(x, 0.f);
}
__device__ __forceinline__ float ex2(float x) { float r; asm("ex2.approx.ftz.f32 %0, %1;" : "=f"(r) : "f"(x)); return r; }
__device__ __forceinline__ float rcp_fast(float x) { float r; asm("rcp.approx.ftz.f32 %0, %1;" : "=f"(r) : "f"(x)); return r; }
__device__ __forceinline__ void red_v4(float* p, float a, float b, float c, float d) {
  asm volatile("red.global.add.v4.f32 [%0], {%1, %2, %3, %4};" :: "l"(p), "f"(a), "f"(b), "f"(c), "f"(d) : "memory");
}
__device__ __forceinline__ uint4 ld_ll(const uint4* p) {
  uint4 v;
  asm volatile("{\n.reg .b64 a, b;\nld.relaxed.gpu.global.v2.b64 {a, b}, [%4];\nmov.b64 {%0, %1}, a;\nmov.b64 {%2, %3}, b;\n}\n"
               : "=r"(v.x), "=r"(v.y), "=r"(v.z), "=r"(v.w) : "l"(p) : "memory");
  return v;
}
__device__ __forceinline__ void st_b64(uint2* p, uint32_t a, uint32_t b) {
  asm volatile("{\n.reg .b64 v;\nmov.b64 v, {%1, %2};\nst.relaxed.gpu.global.b64 [%0], v;\n}\n" :: "l"(p), "r"(a), "r"(b) : "memory");
}
__device__ __forceinline__ void st_b128(uint4* p, uint32_t a, uint32_t b, uint32_t c, uint32_t d) {
  asm volatile("{\n.reg .b128 v;\nmov.b128 v, {%1, %2, %3, %4};\nst.relaxed.gpu.global.b128 [%0], v;\n}\n" :: "l"(p), "r"(a), "r"(b), "r"(c), "r"(d) : "memory");
}
__device__ __forceinline__ uint4 ld_b128(const uint4* p) {
  uint4 v;
  asm volatile("{\n.reg .b128 v;\nld.relaxed.gpu.global.b128 v, [%4];\nmov.b128 {%0, %1, %2, %3}, v;\n}\n" : "=r"(v.x), "=r"(v.y), "=r"(v.z), "=r"(v.w) : "l"(p) : "memory");
  return v;
}

constexpr float LOG2E = 1.4426950408889634f;

struct Params {
  const __nv_bfloat16* x0;
  const __nv_bfloat16* wA_qkv;
  const __nv_bfloat16* wA_o;
  const __nv_bfloat16* wB_qkv;
  const __nv_bfloat16* wB_phi;
  const __nv_bfloat16* wB_o;
  __nv_bfloat16* out;
};

#define ACC_DEF(d, n) _Pragma("unroll") for (int i_ = 0; i_ < (n); i_++) asm volatile("" : "=f"(d[i_]))
#define ACC_FENCE(d, n) _Pragma("unroll") for (int i_ = 0; i_ < (n); i_++) asm volatile("" : "+f"(d[i_]) :: "memory")
#define PIN(a, n) _Pragma("unroll") for (int i_ = 0; i_ < (n); i_++) asm volatile("" : "+f"((a)[i_]))
#define PINU(a, n) _Pragma("unroll") for (int i_ = 0; i_ < (n); i_++) asm volatile("" : "+r"((a)[i_]))

#define V_ADDR(p0, sw) uint32_t va_[2] = {(p0) + (srowoff >> 1) + (lhi ^ lsw2 ^ (sw)), (p0) + (srowoff >> 1) + ((32 + lhi) ^ lsw2 ^ (sw))}
#define STAGE_V(acc) { \
    _Pragma("unroll") for (int j_ = 0; j_ < 4; j_++) { \
      const float* a_ = (acc) + j_ * 8; \
      stsm_x4(va_[j_ & 1] + (j_ >> 1) * 8192, \
              pack_bf16(rs0 * a_[0], rs0 * a_[1]), pack_bf16(rs1 * a_[2], rs1 * a_[3]), pack_bf16(rs0 * a_[4], rs0 * a_[5]), pack_bf16(rs1 * a_[6], rs1 * a_[7])); } }
#define FRAG(dst, acc, TR, grp) { \
    _Pragma("unroll") for (int i_ = 15; i_ >= 0; i_--) { \
      const float r_ = (i_ & 8) ? rs1 : rs0; \
      const uint32_t w_ = pack_bf16(r_ * (acc)[4 * (i_ & 7) + (i_ >> 3) * 2], r_ * (acc)[4 * (i_ & 7) + (i_ >> 3) * 2 + 1]); \
      (dst)[8 + i_] = (TR) ? movm_t(w_) : w_; \
      if (i_ == 8 && warp >= 6 && mm < 15) { \
        _Pragma("unroll") for (int j_ = 0; j_ < 2; j_++) \
          st_b128(g_halo + (size_t)(mm * 8 + jj) * 512 + ((grp) * 4 + warp * 2 - 12 + j_) * 32 + lane, ((dst)[16 + j_ * 4] & ~1u) | H_BIT(l), (dst)[17 + j_ * 4], (dst)[18 + j_ * 4], (dst)[19 + j_ * 4]); } } \
    PINU((dst) + 8, 16); }
#define FRAG_PUT(src, slot) if (warp < 6) { _Pragma("unroll") for (int j_ = 0; j_ < 2; j_++) \
      sts128(sbase + (slot) * SLOT + 2048 + warp * 1024 + j_ * 512 + lane * 16, (src)[j_ * 4], (src)[j_ * 4 + 1], (src)[j_ * 4 + 2], (src)[j_ * 4 + 3]); }
#define FRAG_GET(dst, slot) { _Pragma("unroll") for (int j_ = 0; j_ < 2; j_++) \
      asm volatile("ld.shared.v4.u32 {%0, %1, %2, %3}, [%4];" : "=r"((dst)[j_ * 4]), "=r"((dst)[j_ * 4 + 1]), "=r"((dst)[j_ * 4 + 2]), "=r"((dst)[j_ * 4 + 3]) \
                   : "r"(sbase + (slot) * SLOT + warp * 1024 + j_ * 512 + lane * 16) : "memory"); }
#define RW(j) (((j) >> 1) * 4 + ((j) & 1))
template <int POS> __device__ __forceinline__ float exps16_(float* o, const float* p) {
  float s[4];
#pragma unroll
  for (int j = 0; j < 16; j++) { o[j] = ex2(POS ? p[RW(j)] : -p[RW(j)]); if (j < 4) s[j] = o[j]; else s[j & 3] += o[j]; }
  const float r = (s[0] + s[1]) + (s[2] + s[3]);
  return r + __shfl_xor_sync(0xffffffffu, r, 1);
}
template <int POS> __device__ __forceinline__ void exps16_fix(float* o, const float* p, float& sum) {
  if (__builtin_expect(__any_sync(0xffffffffu, !(sum > SUMLO && sum < SUMHI)), 0)) {
    float m = p[0], q[32];
#pragma unroll
    for (int j = 1; j < 16; j++) m = POS ? fmaxf(m, p[RW(j)]) : fminf(m, p[RW(j)]);
    const float x = __shfl_xor_sync(0xffffffffu, m, 1);
    m = POS ? fmaxf(m, x) : fminf(m, x);
#pragma unroll
    for (int j = 0; j < 16; j++) q[RW(j)] = p[RW(j)] - m;
    sum = exps16_<POS>(o, q);
  }
}
__device__ __forceinline__ void store16(const float* e, float sum, uint32_t dst, uint32_t dsw, int c0) {
  const float inv = rcp_fast(sum);
#pragma unroll
  for (int j = 0; j < 2; j++)
    sts128(dst + (((c0 + j) << 4) ^ dsw), pack_bf16(e[j * 8] * inv, e[j * 8 + 1] * inv), pack_bf16(e[j * 8 + 2] * inv, e[j * 8 + 3] * inv),
           pack_bf16(e[j * 8 + 4] * inv, e[j * 8 + 5] * inv), pack_bf16(e[j * 8 + 6] * inv, e[j * 8 + 7] * inv));
}
template <int POS> __device__ __forceinline__ void expp16(uint32_t* o, float* p) {
  {
#pragma unroll
    for (int r = 0; r < 4; r += 2) {
      float m = p[r];
#pragma unroll
      for (int j = 1; j < 8; j++) m = POS ? fmaxf(m, p[r + RW(j)]) : fminf(m, p[r + RW(j)]);
#pragma unroll
      for (int s = 1; s <= 2; s <<= 1) { const float x = __shfl_xor_sync(0xffffffffu, m, s); m = POS ? fmaxf(m, x) : fminf(m, x); }
#pragma unroll
      for (int j = 0; j < 8; j++) p[r + RW(j)] -= m;
    }
  }
#pragma unroll
  for (int j = 0; j < 8; j++) o[j] = pack_bf16(ex2(POS ? p[2 * j] : -p[2 * j]), ex2(POS ? p[2 * j + 1] : -p[2 * j + 1]));
}
__device__ __forceinline__ void scale32(float* o, const float* p, float c0, float c1) {
#pragma unroll
  for (int i = 0; i < 32; i++) asm volatile("mul.f32 %0, %1, %2;" : "=f"(o[i]) : "f"(p[i]), "f"((i & 2) ? c1 : c0));
}
__device__ __forceinline__ bool any_big(const float* p) {
  float m[4];
#pragma unroll
  for (int i = 0; i < 32; i++) m[i >> 3] = (i & 7) ? fmaf(p[i], p[i], m[i >> 3]) : p[i] * p[i];
  return __any_sync(0xffffffffu, !(fmaxf(fmaxf(m[0], m[1]), fmaxf(m[2], m[3])) < BIGLIM));
}
__device__ __forceinline__ void phiq_a(float* p, bool big) {
  if (__builtin_expect(!big, 1)) {
#pragma unroll
    for (int j = 0; j < 16; j++) p[j] = ex2(p[j]);
  }
}
template <int NEXT> __device__ __forceinline__ void phiq_b(uint32_t* o, float* p, bool big) {
  if (__builtin_expect(big, 0)) {
    expp16<0>(o, p); expp16<1>(o + 8, p);
  } else {
    if (NEXT) phiq_a(p + 16, false);
#pragma unroll
    for (int j = 0; j < 4; j++) {
      const float a = p[4 * j], b = p[4 * j + 1], c = p[4 * j + 2], d = p[4 * j + 3];
      const float ab = a * b, cd = c * d, r = rcp_fast(ab * cd), x = r * cd, y = r * ab;
      o[2 * j] = pack_bf16(x * b, x * a); o[2 * j + 1] = pack_bf16(y * d, y * c);
      o[8 + 2 * j] = pack_bf16(a, b); o[9 + 2 * j] = pack_bf16(c, d);
    }
  }
}
#define SCHED_FENCE() asm volatile("pmevent 0;" ::: "memory")

__global__ void __cluster_dims__(2, 1, 1) __launch_bounds__(384, 1)
mega_kernel(const __grid_constant__ CUtensorMap tm_x0, const __grid_constant__ CUtensorMap tm_xo, const __grid_constant__ CUtensorMap tm_os,
            const __grid_constant__ CUtensorMap tm_o, const __grid_constant__ CUtensorMap tm_wf,
            const __grid_constant__ CUtensorMap tm_wqA, const __grid_constant__ CUtensorMap tm_wqB,
            const __grid_constant__ CUtensorMap tm_woA, const __grid_constant__ CUtensorMap tm_woB,
            const __grid_constant__ CUtensorMap tm_phi, const Params prm) {
  extern __shared__ __align__(1024) uint8_t smem_raw[];
  const uint32_t sbase = smem_u32(smem_raw);
  const uint32_t bar_full = sbase + OFF_BAR;
  const uint32_t bar_done = bar_full + 384;
  const uint32_t bar_stat = bar_full + 768, bar_stat2 = bar_full + 776, bar_epi = bar_full + 784, bar_phi = bar_full + 936  , bar_halo = bar_full + 904  ;
  const uint32_t bar_xr = bar_full + 800, bar_lx = bar_full + 808, bar_stg = bar_full + 832;
  const uint32_t bar_chk = bar_full + 848;

  const int warp = __shfl_sync(0xffffffffu, threadIdx.x >> 5, 0), lane = threadIdx.x & 31;
  const uint32_t bar_kx = sbase + OFF_ID + 384 + warp * 8;
  uint32_t rank;
  asm volatile("mov.u32 %0, %%cluster_ctarank;" : "=r"(rank));
  const int aux = (int)blockIdx.x - NMAIN, tp = (int)(blockIdx.x >> 1) - 4;
  const int gp = tp < 0 ? 0 : (tp < 32 ? tp & 7 : 1 + (tp - 32) % 7), me = tp < 0 ? tp + 8 : (tp < 32 ? tp >> 3 : 4 + (tp - 32) / 7);
  const int jj = me, cc = gp;
  const int cta = aux >= 0 ? -1 : (cc * 8 + jj) * 2 + (int)rank;
  const int mm = cc * 2 + (int)rank;

#define LOAD_EPOCH() const unsigned epoch = ld_relaxed(&g_flags.epoch.v), ep1 = epoch + 1; (void)epoch
  int budget = 1 << 22;

  if (cta >= 0) {
    if (warp >= 8 && warp < 8 + EARLY && elect_one()) {
      const int u = warp - 8;
      const uint32_t fb = bar_full + u * 8;
      mbar_init(fb, 1);
      asm volatile("fence.mbarrier_init.release.cluster;" ::: "memory");
      fence_proxy_async_smem();
      mbar_expect_tx(fb, QST + SLOT);
      if (u) __nanosleep(STAG2);
      tma_load_t(sbase + OFF_S + u * SLOT, &tm_x0, fb, jj * 128 + u * 64, mm * 128);
#pragma unroll
      for (int i = 0; i < 6; i++) tma_load_2d(sbase + u * QST + i * 4096, &tm_wqA, fb, jj * 128 + (i >> 1) * 1024, jj * 128 + u * 64 + (i & 1) * 32);
      if (u == 0) PROFT(472);
    }
    __syncwarp();
    {
      const int tx = threadIdx.x;
      const __nv_bfloat16* pf = (tx < 128) ? prm.x0 + (size_t)(mm * 128 + tx) * D_MODEL + jj * 128
                                           : prm.wA_qkv + (size_t)(jj * 128 + (tx & 63)) * 3072 + ((tx - 128) >> 6) * 1024 + jj * 128 + rank * 64;
      if (tx < 320) asm volatile("prefetch.global.L2 [%0];" :: "l"(pf));
      else if (tx == 320) prefetch_tmap(&tm_x0);
      else if (tx == 352) prefetch_tmap(&tm_wqA);
      else if (tx == 383) asm volatile("prefetch.global.L2 [%0];" :: "l"(&g_flags.epoch.v));
    }
    if (elect_one()) {
#pragma unroll
      for (int i = 0; i < 4; i++) {
        const int u = warp * 4 + i;
        if (u >= EARLY) mbar_init(bar_full + u * 8, ((u >= 4 && u < 11) || (u > 32 && u != 40)) ? 2 : 1); mbar_init(bar_done + u * 8, 16);
      }
      mbar_init(bar_stat + warp * 16, 0x111111181182ull >> (4 * warp) & 15);
      mbar_init(bar_stat + warp * 16 + 8, 0x111111121811ull >> (4 * warp) & 15);
      mbar_init(bar_chk + 112 + (warp & 7) * 8, 1);
      mbar_init(bar_kx, 1);
      asm volatile("fence.mbarrier_init.release.cluster;" ::: "memory");
    }
    __syncwarp();
    __syncthreads();
    asm volatile("barrier.cluster.arrive.relaxed.aligned;" ::: "memory");
  }

  if (cta < 0) {
    LOAD_EPOCH();
    const uint32_t buf = sbase + warp * SLOT, bar = sbase + OFF_BAR + warp * 16;
    const uint32_t lsw = (lane & 7) << 4, lhi = (lane >> 4) << 4, lrow = (lane & 15) * 128;
    const bool el = elect_one();
    if (el) {
      mbar_init(bar, 1); mbar_init(bar + 8, 1);
      asm volatile("fence.mbarrier_init.release.cluster;" ::: "memory");
    }
#pragma unroll 1
    for (int rd = 0; rd < (NLAYERS > 1 ? 5 : 2); rd++) {
      if (rd >= 2 && warp >= 8) break;
      const int tk = rd < 2 ? aux * 12 + warp : aux * 8 + warp;
      const int half = tk & 1;
      const int blk = rd < 2 ? (tk >> 1) * 2 + rd : (4 - rd) * 16 + (tk >> 1);
      const CUtensorMap* tm = rd < 2 ? &tm_wqA : (rd == 2 ? &tm_wqB : &tm_wf);
      const int j0 = (blk & 15) >> 1;
#define AUX_LOAD(n) { const uint32_t d_ = buf + ((n) & 1) * 8192, b_ = bar + ((n) & 1) * 8; const int r_ = kslice(j0, 2 * (n) + half) * 64; \
        mbar_expect_tx(b_, 8192); tma_load_2d(d_, tm, b_, blk * 64, r_); tma_load_2d(d_ + 4096, tm, b_, blk * 64, r_ + 32); }
      if (el) {
        if (rd == 3) { wait_flag(&g_flags.wfready[j0].v, ep1 * 16); fence_proxy_async_global(); }
        AUX_LOAD(0); AUX_LOAD(1);
      }
      __syncwarp();
      float cs[8][4];
#pragma unroll
      for (int i = 0; i < 8; i++) cs[i][0] = cs[i][1] = cs[i][2] = cs[i][3] = 0.f;
#pragma unroll 1
      for (int n = 0; n < 8; n++) {
        const uint32_t tb = buf + (n & 1) * 8192 + lrow;
        mbar_wait(bar + (n & 1) * 8, (n >> 1) & 1);
#pragma unroll
        for (int i = 0; i < 16; i++) {
          uint32_t b0, b1, b2, b3;
          ldsm_x4_t(tb + (i >> 2) * 2048 + (((i & 3) * 32 + lhi) ^ lsw), b0, b1, b2, b3);
          mma_bf16(cs[2 * (i & 3)], 0x3F803F80u, 0x3F803F80u, 0x3F803F80u, 0x3F803F80u, b0, b1);
          mma_bf16(cs[2 * (i & 3) + 1], 0x3F803F80u, 0x3F803F80u, 0x3F803F80u, 0x3F803F80u, b2, b3);
        }
        __syncwarp();
        if (el && n < 6) AUX_LOAD(n + 2);
        __syncwarp();
      }
      if (lane < 4) {
#pragma unroll
        for (int i = 0; i < 8; i++) st_b64(&g_colsum[rd >= 2][blk * 32 + i * 4 + lane][half], __float_as_uint(cs[i][0]), (__float_as_uint(cs[i][1]) & ~3u) | (ep1 & 3));
      }
      __syncwarp();
    }
  } else if (warp >= 8) {
    asm volatile("setmaxnreg.dec.sync.aligned.u32 40;");
    if (warp == 8) {
      const bool el = elect_one();
      cluster_wait();
      if (el) {
#pragma unroll 1
        for (int l = 0; l < NLAYERS; l++) {
          const uint32_t par = l & 1;
          const CUtensorMap* tqk = par ? &tm_wf : &tm_wqA;
          const CUtensorMap* tv = par ? &tm_wqB : &tm_wqA;
          const CUtensorMap* two = par ? &tm_woB : &tm_woA;
          if (l == 1) { LOAD_EPOCH(); wait_flag(&g_flags.wfready[jj].v, ep1 * 16); fence_proxy_async_global(); }
#pragma unroll 1
          for (int u = l ? 0 : EARLY; u < 32; u++) {
            if (u >= 4) mbar_wait_sl(bar_done + (u - 4) * 8, par);
            else if (l) mbar_wait_sl(bar_done + (43 + u + (u >> 1)) * 8, par ^ 1);
            else mbar_wait_sl(bar_full, 0);
            const uint32_t fb = bar_full + u * 8;
            const bool res = u < 11 || (u >= 18 && u < 22);
            mbar_expect_tx(fb, res ? QST : QST + SLOT);
            const int row = kslice(jj, u < 4 ? u & 1 : (u < 18 ? u - 2 : (u < 22 ? u - 6 : u - 20))) * 64 + (int)rank * 32;
            const int ps = u < 4 ? u >> 1 : (u >= 18), col = jj * 128 + ps * 64;
            const int c0 = par ? jj * 128 + (ps ? 0 : 1024) : col;
            const uint32_t dst = sbase + (u & 3) * QST + rank * 4096;
            tma_load_2d_mc(dst, tqk, fb, c0, row);
            tma_load_2d_mc(dst + 8192, tqk, fb, c0 + (par ? 64 : 1024), row);
            tma_load_2d_mc(dst + 16384, tv, fb, col + 2048, row);
            if (l == PRL && u >= PRU && u < PRU + 4) PROFT(473 + u - PRU);
          }
#pragma unroll 1
          for (int s = 0; s < 16; s++) {
            if (s < 5) { if (s != 2 && s != 4) mbar_wait_sl(bar_done + (28 + s) * 8, par); }
            else if (s != 14) mbar_wait_sl(bar_done + (27 + s - (s == 15)) * 8, par);
            const uint32_t fb = bar_full + (32 + s) * 8;
            mbar_expect_tx(fb, SLOT);
            tma_load_2d_mc(sbase + rank * 8192 + (uint32_t)((WO_BSLOT >> (4 * s)) & 15) * SLOT, two, fb, jj * 128 + (int)rank * 64, wslice(jj, s) * 64);
            const int ts = s + par;
            if (s >= 5 && ts < 8) {
              mbar_expect_tx(bar_chk - 8 + ts * 8, SLOT);
              tma_load_t(sbase + (uint32_t)((WO_ASLOT(par) >> (4 * ts)) & 15) * SLOT, &tm_o, bar_chk - 8 + ts * 8, wslice(jj, ts) * 64, mm * 128);
            }
          }
        }
      }
      __syncwarp();
    } else if (warp == 9) {
      const bool el = elect_one();
      LOAD_EPOCH();
#pragma unroll 1
      for (int lp = 0; lp < 4 * NLAYERS; lp++) {
        const int l = lp >> 2, ph = lp & 3;
        if (ph == 3) continue;
        const uint32_t par = l & 1;
        const unsigned* pp = reinterpret_cast<const unsigned*>(g_obuf + (ph >> 1) * 64 + (size_t)(mm * 128 + (ph ? 0 : S_LEN) + ((lane & 7) | PROWS) * 16 + (jj & 1) * 8) * D_MODEL +
                                                               (jj >> 1) * 16 + srcb(jj, lane >> 3) * 128);
        const CUtensorMap* tm = lp ? &tm_o : &tm_x0;
        const int row = mm * 128 + ((ph || !l) ? 0 : S_LEN);
        const uint32_t bit = ph ? O_BIT(l) : X_BIT(l - 1);
        const uint32_t slots = ph ? (uint32_t)(WO_ASLOT(par) >> (ph * 32 - 28)) : 0x8769876u;
        const unsigned long long fr = ph == 0 ? XPACE : ph == 1 ? (par ? FRB : 0x35351F1Eull) : (par ? 0x27262524232232ull : 0x27262524233232ull);
        uint32_t no = (lp == 0 || (lp & 7) == 1) ? 0 : (ph == 1 ? NOB : (ph ? NO1 : NOX)), v0 = 0, v1 = 0;
        mbar_wait_sl(ph ? bar_done + ((uint32_t)fr & 63) * 8 : (l ? bar_done + 47 * 8 : bar_full), ph ? par : (l ? par ^ 1 : 0));
        if (el && ph) PROFT(324 + l * 16 + ph);
        __syncwarp();
        if (no && (ph == 1 ? SPD1 : (ph ? SPD2 : SPD0))) __nanosleep(ph == 1 ? SPD1 : (ph ? SPD2 : SPD0));
        if (no) { v0 = ld_relaxed(pp); __nanosleep(POLLGAP); v1 = ld_relaxed(pp); }
#pragma unroll 1
        for (int i = 0; i < (ph == 1 ? 4 + par : 7); i++, no >>= 8) {
#pragma unroll 1
          for (int it = 0; (no & 0xFF) && it < (1 << 18); it++) {
            no &= __ballot_sync(0xffffffffu, (v0 ^ bit) & 1) >> (8 * i);
            if (no) v0 = ld_relaxed(pp);
            if (!(no & 0xFF)) break;
            no &= __ballot_sync(0xffffffffu, (v1 ^ bit) & 1) >> (8 * i);
            if (no) v1 = ld_relaxed(pp);
          }
          if (ph || i >= XP0) mbar_wait_sl(bar_done + ((uint32_t)(fr >> (8 * i)) & 63) * 8, par);
          if (el) {
            if (i == 0) PROFT(320 + l * 16 + ph);
            const uint32_t cb = (lp ? bar_chk + (ph >> 1) * 112 : bar_full + 32) + i * 8;
            mbar_expect_tx(cb, SLOT);
            tma_load_t(sbase + ((slots >> (4 * i)) & 15) * SLOT, tm, cb, srcb(jj, i) * 128 + (ph >> 1) * 64, row);
          }
          __syncwarp();
        }
        if (ph == 0 && el) {
          if (l) { wait_flag(&g_flags.xready[l][mm].v, ep1 * 8); fence_proxy_async_global(); }
#pragma unroll 1
          for (int u = 11; u < 34; u++) {
            if (u == 18) u = 22;
            mbar_wait_sl(bar_done + (u - 4) * 8, par);
            if (u == 32) mbar_expect_tx(bar_xr, 2 * SLOT);
            tma_load_t(sbase + OFF_RA + (u & 3) * SLOT, tm, u < 32 ? bar_full + u * 8 : bar_xr, kslice(jj, u < 18 ? u - 2 : (u < 32 ? u - 20 : u - 32)) * 64, row);
          }
        }
        __syncwarp();
      }
      if (el && atomicAdd(&g_flags.done.v, 1) == ep1 * NMAIN - 1) asm volatile("st.relaxed.gpu.global.u32 [%0], %1;" :: "l"(&g_flags.epoch.v), "r"(ep1) : "memory");
      __syncwarp();
      cluster_wait();
    } else {
      const int hw = warp - 10;
      LOAD_EPOCH();
      const bool el = elect_one();
      cluster_wait();
      if (hw == 0) {
        mbar_wait_sl(bar_full + 8, 0);
        if (lane < 7) prefetch_tmap(lane == 0 ? &tm_os : lane == 1 ? &tm_o : lane == 2 ? &tm_wf : lane == 3 ? &tm_wqB : lane == 4 ? &tm_woA : lane == 5 ? &tm_woB : &tm_phi);
#pragma unroll 1
        for (int i = 0; i < (NLAYERS > 1 ? 9 : 0); i++) {
          if (i == 0 || i == 5) mbar_wait_sl(bar_done + (i ? FD1 : FD0) * 8, 0);
          if (el) {
            if (i == 0) { mbar_expect_tx(bar_phi, 2 * SLOT + 8192); tma_load_2d(sbase + OFF_PHI, &tm_phi, bar_phi, 0, jj * 128); }
            else tma_load_2d(sbase + (i > 4 ? 10 : 12) * SLOT - 4096 + i * 4096, &tm_wqB, bar_phi, (i > 4 ? 896 : 0) + jj * 128 + ((i - 1) >> 1) * 64, mm * 64 + (~i & 1) * 32);
          }
          __syncwarp();
          __nanosleep(PFGAP);
        }
      } else {
        if (lane < 24) {
          const uint32_t one = (lane & 8) ? 0u : 0x3F80u << ((lane & 1) * 16), w = (lane >> 1) & 3;
          sts128(sbase + OFF_ID + lane * 16, w == 0 ? one : 0u, w == 1 ? one : 0u, w == 2 ? one : 0u, w == 3 ? one : 0u);
        }
#pragma unroll 1
        for (int b = 0; b < 2; b++) {
          float4* z = reinterpret_cast<float4*>(g_kv[b] + (jj * 4) * KVH + mm * (4 * KVH / 16)) + lane;
#pragma unroll
          for (int i = 0; i < 6; i++) z[i * 32] = make_float4(0.f, 0.f, 0.f, 0.f);
        }
#pragma unroll 1
        for (int i = 0; i < 16; i++) {
          const int b = i >> 2;
          const uint32_t v = (b == 0 ? O_BIT(0) : b == 1 ? X_BIT(0) : H_BIT(0)) + 1;
          uint4* p = b < 2 ? reinterpret_cast<uint4*>(g_obuf + (size_t)(b * S_LEN + mm * 128 + (i & 3) * 32 + (lane >> 3) * 8) * D_MODEL + jj * 128 + (b ? 0 : 64)) + (lane & 7)
                           : g_halo + (size_t)(mm * 8 + jj) * 512 + i * 32 + lane;
          *p = make_uint4(v, v, v, v);
        }
        fence_proxy_async_global();
      }
      __syncwarp();
      uint32_t chkp = 0;
#pragma unroll 1
      for (int lp = hw; lp < 8 * NLAYERS; lp++) {
        const int l = lp >> 3, tk = lp & 7, ph = tk ? 2 - hw : 0;
        const uint32_t par = l & 1;
        int lane; asm volatile("mov.u32 %0, %%laneid;" : "=r"(lane));
        if (tk == 5 || (hw && tk == 0)) {
          const uint32_t bit = ph ? O_BIT(l) : X_BIT(l - 1);
          uint32_t slots = ph ? (uint32_t)(WO_ASLOT(par) >> (ph * 32 - 28)) : 0x8769876u;
          const uint32_t a0 = sbase + (lane & 7) * 126 + lane * 4 + (lane & 1) * 14;
#pragma unroll 1
          for (int c = 0; c < 7; c++, slots >>= 4) {
            const uint32_t cb = bar_chk + 112 - hw * 112 + c * 8;
#pragma unroll 1
            for (int it = 0; it < (1 << 12); it++) {
              mbar_wait_sl(cb, (chkp >> c) & 1);
              chkp ^= 1u << c;
              if (el && c == 0) PROFT(ph == 1 ? 480 + l * 2 : 488 + l * 2 + (ph >> 1));
              uint32_t bad;
              asm volatile("{\n.reg .b32 w<16>;\n"
                           "ld.shared.u32 w0, [%1 + 0];\n"
                           "ld.shared.u32 w1, [%1 + 1024];\n"
                           "ld.shared.u32 w2, [%1 + 2048];\n"
                           "ld.shared.u32 w3, [%1 + 3072];\n"
                           "ld.shared.u32 w4, [%1 + 4096];\n"
                           "ld.shared.u32 w5, [%1 + 5120];\n"
                           "ld.shared.u32 w6, [%1 + 6144];\n"
                           "ld.shared.u32 w7, [%1 + 7168];\n"
                           "ld.shared.u32 w8, [%1 + 8192];\n"
                           "ld.shared.u32 w9, [%1 + 9216];\n"
                           "ld.shared.u32 w10, [%1 + 10240];\n"
                           "ld.shared.u32 w11, [%1 + 11264];\n"
                           "ld.shared.u32 w12, [%1 + 12288];\n"
                           "ld.shared.u32 w13, [%1 + 13312];\n"
                           "ld.shared.u32 w14, [%1 + 14336];\n"
                           "ld.shared.u32 w15, [%1 + 15360];\n"
                           "lop3.b32 w0, w0, w1, %2, 0x7E;\n"
                           "lop3.b32 w2, w2, w3, %2, 0x7E;\n"
                           "lop3.b32 w4, w4, w5, %2, 0x7E;\n"
                           "lop3.b32 w6, w6, w7, %2, 0x7E;\n"
                           "lop3.b32 w8, w8, w9, %2, 0x7E;\n"
                           "lop3.b32 w10, w10, w11, %2, 0x7E;\n"
                           "lop3.b32 w12, w12, w13, %2, 0x7E;\n"
                           "lop3.b32 w14, w14, w15, %2, 0x7E;\n"
                           "lop3.b32 w0, w0, w2, w4, 0xFE;\nlop3.b32 w6, w6, w8, w10, 0xFE;\nlop3.b32 w0, w0, w12, w14, 0xFE;\nlop3.b32 %0, w0, w6, 1, 0xA8;\n}\n"
                           : "=r"(bad) : "r"(a0 + (slots & 15) * SLOT), "r"(bit) : "memory");
              if (__all_sync(0xffffffffu, bad == 0)) break;
              if (el) {
                fence_proxy_async_smem();
                mbar_expect_tx(cb, SLOT);
                tma_load_t(sbase + (slots & 15) * SLOT, &tm_o, cb, srcb(jj, c) * 128 + (ph >> 1) * 64, mm * 128 + (ph ? 0 : S_LEN));
                RETRY_COUNT();
              }
              __syncwarp();
            }
            if (el) { mbar_arrive_local(bar_full + (c + (ph ? 25 + ph * 8 : 4)) * 8); if (lp == PRL * 8 && c == 0) PROFT(477); }
            __syncwarp();
          }
        } else if (hw && (tk & 5) == 1) {
          {
            const int hp = tk >> 1;
            const uint4* src = reinterpret_cast<const uint4*>(g_colsum[par][jj * 64 + hp * 32 + lane]);
            uint32_t bad;
            int it = 0;
            float c[6];
            do {
              bad = 0;
#pragma unroll
              for (int p = 0; p < 3; p++) {
                const uint4 v = ld_ll(src + ((par && p < 2) ? (hp ? -32 : 512) + p * 32 : p * 512));
                bad |= (v.y ^ ep1) | (v.w ^ ep1);
                c[2 * p] = __uint_as_float(v.x) + __uint_as_float(v.z); c[2 * p + 1] = __uint_as_float(v.y) + __uint_as_float(v.w);
              }
              bad &= 3;
              if (bad) __nanosleep(300);
            } while (bad && ++it < (1 << 16));
#pragma unroll
            for (int p = 0; p < 6; p++) {
              uint32_t h, m, lo;
              split3(c[p], h, m, lo);
              sts128(sbase + OFF_LNB + hp * 4096 + (p >> 1) * 1024 + lane * 32 + (p & 1) * 16, h | (m << 16), h | (lo << 16), h | (m << 16), lo | (m << 16));
            }
            fence_proxy_async_smem();
            __syncwarp();
            if (el) { mbar_arrive_local(hp ? bar_stat2 : bar_stat); if (hp == 0) PROFT(324 + l * 16); }
            __syncwarp();
          }
        } else if (tk == 0) {
          mbar_wait_sl(bar_done + 24, par);
          const uint4* sp = reinterpret_cast<const uint4*>(g_stats + (size_t)(mm * 128) * 8) + lane;
#pragma unroll 1
          for (int hf = 0; hf < 4; hf++) {
            uint4 v[4];
            uint32_t bad;
            int it = 0;
            do {
              bad = 0;
#pragma unroll
              for (int i = 0; i < 4; i++) { v[i] = ld_ll(sp + (hf * 4 + i) * 32); bad |= (v[i].y ^ STAT_TAG(l)) | (v[i].w ^ STAT_TAG(l)); }
              bad &= 3;
              if (bad) __nanosleep(200);
            } while (bad && ++it < (1 << 16));
            __syncwarp();
            float mean = 0.f, m2 = 0.f;
#pragma unroll
            for (int i = 0; i < 4; i++) {
              float a = __uint_as_float(v[i].x) + __uint_as_float(v[i].z);
              a += __shfl_xor_sync(0xffffffffu, a, 1); a += __shfl_xor_sync(0xffffffffu, a, 2);
              a *= 0.125f;
              const float e0 = __uint_as_float(v[i].x) - a, e1 = __uint_as_float(v[i].z) - a;
              float q = fmaf(fmaf(e0, e0, e1 * e1), 128.f, __uint_as_float(v[i].y) + __uint_as_float(v[i].w));
              q += __shfl_xor_sync(0xffffffffu, q, 1); q += __shfl_xor_sync(0xffffffffu, q, 2);
              if ((lane & 3) == i) { mean = a; m2 = q; }
            }
            const uint32_t row = hf * 32 + (lane & 3) * 8 + (lane >> 2);
            uint32_t h, m, lo;
            split3(-0.5f * mean, h, m, lo);
            sts128(sbase + OFF_LNA + row * 16, h | (h << 16), m | (h << 16), lo | (m << 16), m | (lo << 16));
            sts32f(sbase + OFF_ST + row * 4, rsqrtf(m2 * (1.f / 1024.f) + 1e-5f));
          }
          fence_proxy_async_smem();
          __syncwarp();
          if (el) { mbar_arrive_local(bar_stat); PROFT(323 + l * 16); }
          __syncwarp();
#pragma unroll 1
          for (int i = 0; i < 8 - 4 * l; i++) {
            asm volatile("prefetch.global.L2 [%0];" :: "l"(i < 4 ? (l ? prm.wB_o : prm.wA_o) + (size_t)cta * 8192 + i * 2048 + lane * 64
                                                                 : prm.wB_qkv + (size_t)(cta * 8 + (i - 4) * 2 + (lane >> 4)) * 3072 + 2048 + (lane & 15) * 64));
            __nanosleep(PFGAP);
          }
        } else if (lp == 3) {
#pragma unroll 1
          for (int c = 0; c < (NLAYERS > 1 ? 8 : 0); c++) {
            if (!(c & 3)) asm volatile("bar.sync %0, 288;" :: "r"(BAR_WF + (c >> 2)) : "memory");
            if (el) {
              tma_store_2d(&tm_wf, sbase + 11 * SLOT + c * 4096, (c < 4 ? 1024 : -128) + jj * 128 + (c >> 1) * 64, mm * 64 + (c & 1) * 32);
              if ((c & 3) == 3) {
                asm volatile("cp.async.bulk.commit_group;\ncp.async.bulk.wait_group.read 0;" ::: "memory");
                mbar_arrive_local(bar_phi + (c >> 2) * 8);
              } else __nanosleep(WFGAP);
            }
            __syncwarp();
          }
          if (el) { bulk_commit_wait(); signal_release(&g_flags.wfready[jj].v); PROFT(335); }
          __syncwarp();
        } else if (tk == 2 || tk == 4) {
          if (par) continue;
          const int i = tk >> 2;
          mbar_wait_sl(bar_done + (i ? HW1 : (hw ? 19 : HW0)) * 8, 0);
          const uint4* src = g_halo + (size_t)(mm * 8 + jj - 8) * 512 + i * 256 + hw * 128 + lane;
          uint4 v[4];
          int it = 0;
          bool ok;
          do {
#pragma unroll
            for (int j = 0; j < 4; j++) v[j] = mm ? ld_b128(src + j * 32) : make_uint4(H_BIT(l), 0, 0, 0);
            ok = __all_sync(0xffffffffu, (((v[0].x ^ H_BIT(l)) | (v[1].x ^ H_BIT(l)) | (v[2].x ^ H_BIT(l)) | (v[3].x ^ H_BIT(l))) & 1) == 0);
          } while (!ok && ++it < (1 << 16));
          if (lp + hw == 3 && NLAYERS > 1) mbar_wait_sl(bar_phi, 1);
#pragma unroll
          for (int j = 0; j < 4; j++) sts128(sbase + OFF_S + hw * SLOT + j * 512 + lane * 16, v[j].x, v[j].y, v[j].z, v[j].w);
          __syncwarp();
          if (el) { mbar_arrive_local(bar_halo + hw * 8); PROFT(331 + l * 16 + i * 2 + hw); }
          __syncwarp();
        } else if (tk == 6 && hw == 0 && l < NLAYERS - 1) {
          bar_sync<BAR_X1, 288>();
          if (el) {
            PROFT(328 + l * 16);
            mbar_wait_sl(bar_full + XD * 8, par ^ 1);
            tma_store_t(&tm_o, sbase + 11 * SLOT, jj * 128 + 64, mm * 128 + S_LEN);
            bulk_commit_wait();
            signal_release(&g_flags.xready[l + 1][mm].v);
            PROFT(330 + l * 16);
          }
          __syncwarp();
        }
      }
    }
    cluster_sync();
  } else {
    asm volatile("setmaxnreg.inc.sync.aligned.u32 232;");
    const int wg = warp >> 2;
    const int r0 = warp * 16;
    const uint32_t pK = sbase + OFF_S, pV = sbase + OFF_S + SLOT;
#define PMASKS(on, bit) const uint32_t pm0 = ((on) && t == (g >> 1)), pbit = (bit)
#define PBIT(w) (((w) & ~pm0) | (pbit & pm0))
#define LANE_CONSTS() \
    int lane; asm volatile("mov.u32 %0, %%laneid;" : "=r"(lane)); \
    const int g = lane >> 2, t = lane & 3; \
    const uint32_t srowoff = (r0 + (lane & 15)) * 128, lsw = (lane & 7) << 4, lhi = (lane >> 4) << 4, lsw2 = (lane & 6) << 3; \
    (void)g; (void)t; (void)srowoff; (void)lsw; (void)lhi; (void)lsw2;
    uint32_t stgp = 0, peer;
    asm volatile("mapa.shared::cluster.u32 %0, %1, %2;" : "=r"(peer) : "r"(sbase), "r"(rank ^ 1));
    peer -= sbase;
    const uint32_t dA0 = (((sbase & 0x3FFFF) + wg * 8192) >> 4) | 0x10000u, dB0 = ((sbase & 0x3FFFF) >> 4) | 0x2000000u;
    cluster_wait();
#define DESC(lo, hi) ((uint64_t)(uint32_t)(lo) | ((uint64_t)(hi) << 32))
#define STG_ARRIVE() { __syncwarp(); if (elect_one()) mbar_arrive_local(bar_stg); }
#define STG_WAIT() { mbar_wait(bar_stg, stgp); stgp ^= 1; }
#define PROFS() do {} while (0)
#define REL(addr) { if (elect_one()) { mbar_arrive_local(addr); asm volatile("mbarrier.arrive.shared::cluster.b64 _, [%0];" :: "r"((addr) + peer) : "memory"); } }
#define QSTEP(ACC, DA, SC) { \
      const uint32_t da = (DA), db = dB0 + (ub & 0x18) * (QST >> 7); \
      mbar_wait(ub, par); \
      wgmma_fence(); \
      wgmma4_n192<SC>(ACC, da, db); \
      wgmma_commit(); PROFS(); }
#define QREL() { wgmma_wait<1>(); REL(ub + 376); ub += 8; }
#define RA_CUR (dA0 + (OFF_RA >> 4) + (ub & 0x18) * (SLOT >> 7))
#define PUMP1() { QSTEP(S1, RA_CUR, 1); QREL(); }
#define PUMP0() { PUMP1(); SCHED_FENCE(); }
#define PUMP() if (h == 0) PUMP1()
#define WSTEP() { \
      const uint32_t s4 = (ub - bar_full - 256) >> 1; \
      const uint32_t da = dA0 + (((uint32_t)(WO_ASLOT(par) >> s4) & 15) << 10), db = dB0 + (((uint32_t)(WO_BSLOT >> s4) & 15) << 10); \
      mbar_wait(ub, par); \
      wgmma_fence(); \
      wgmma4_n128<1>(S1, da, db); \
      wgmma_commit(); PROFS(); \
      wgmma_wait<1>(); \
      if (s4) REL(ub + 376); \
      ub += 8; }
#define PUMPS(n) { _Pragma("unroll 1") for (int i_ = 0; i_ < (n); i_++) PUMP1(); }
#define LNSTEP(ACC, hh) { wgmma_fence(); wgmma_n192<1, 0>(ACC, make_desc(sbase + OFF_LNA + wg * 1024, 0, 128) ^ (1ull << 62), make_desc(sbase + OFF_LNB + (hh) * 4096, 0, 128) ^ (1ull << 62)); }
#define WARP_STORE(tm, tile, col, row) { fence_proxy_async_smem(); __syncwarp(); \
      if (elect_one()) { tma_store_2d(tm, (tile) + r0 * 128, col, (row) + r0); asm volatile("cp.async.bulk.commit_group;" ::: "memory"); } __syncwarp(); }
#define TILE_CONSTS(base, on, bit) \
      uint32_t ta[5]; \
      { PMASKS(on, bit); (void)pbit; ta[4] = pm0; } \
      _Pragma("unroll") for (int j = 0; j < 4; j++) ta[j] = (base) + srowoff + ((((uint32_t)j << 5) + lhi) ^ lsw); \
      PINU(ta, 5); SCHED_FENCE(); \
      const uint32_t pm0 = ta[4], pbit = (bit)
#define X_OUT(pc, W) { \
      _Pragma("unroll") for (int j = 0; j < 4; j++) \
        stsm_x4(ta[j] + (pc) * SLOT, \
                PBIT(pack_bf16((W)[j * 8 + 0], (W)[j * 8 + 1])), PBIT(pack_bf16((W)[j * 8 + 2], (W)[j * 8 + 3])), \
                (pack_bf16((W)[j * 8 + 4], (W)[j * 8 + 5])), (pack_bf16((W)[j * 8 + 6], (W)[j * 8 + 7]))); }
#define REST_P1(SKEW) { \
      mbar_wait(bar_stat2, par); \
      LNSTEP(S1, 1); \
      _Pragma("unroll 1") while (ub < bar_full + 256) { \
        if (ub == bar_full + 256 - 8 * (SKEW) && wg == 0) bar_sync<BAR_SKEW, 256>(); \
        QSTEP(S1, RA_CUR, 1); \
        if (ub == bar_full + 248 && wg == 1) bar_arrive<BAR_SKEW, 256>(); \
        QREL(); \
      } \
      mbar_wait(bar_done + (31 - (SKEW)) * 8, par);        \
      wgmma_wait<0>(); \
      ACC_FENCE(S1, 96); \
      REL(bar_done + 31 * 8); \
      PROF(13); }
#define FOLD(tile, rd) { \
          LANE_CONSTS(); \
          float d[32]; \
          ACC_DEF(d, 32); \
          mbar_wait(bar_phi, 0); \
          wgmma_fence(); \
          _Pragma("unroll") for (int i = 0; i < 2; i++) { \
            const uint64_t da = make_desc((tile) + wg * 8192 + i * 64, 16, 1024); \
            const uint64_t db = make_desc(sbase + OFF_PHI + wg * 4096 + i * 2048, 16, 512) ^ (3ull << 62); \
            wgmma_n32<0>(d + i * 16, da, db); wgmma_n32<1>(d + i * 16, da + 2, db + 64); \
          } \
          wgmma_commit(); \
          PUMP0(); \
          ACC_FENCE(d, 32); \
          bar_wg(wg); \
          _Pragma("unroll") for (int i = 0; i < 4; i++) { \
            const float* x = d + (i & 1) * 8 + (i >> 1) * 2; \
            if (rd) sts128((tile) + wg * 8192 + ((warp & 3) * 16 + (i >> 1) * 8 + g) * 128 + (((2 * t + (i & 1)) ^ g) << 4), \
                           pack_bf16(x[0], x[1]), pack_bf16(x[4], x[5]), pack_bf16(x[16], x[17]), pack_bf16(x[20], x[21])); \
            else stsm_x4((tile) + srowoff + ((((uint32_t)i << 5) + lhi) ^ lsw), pack_bf16(d[i * 8], d[i * 8 + 1]), pack_bf16(d[i * 8 + 2], d[i * 8 + 3]), \
                         pack_bf16(d[i * 8 + 4], d[i * 8 + 5]), pack_bf16(d[i * 8 + 6], d[i * 8 + 7])); \
          } \
          }
#define XM_ISSUE() { mbar_wait(bar_xr, par); wgmma_fence(); \
      wgmma_copy(T_, dA0 + (OFF_RA >> 4), make_desc(sbase + OFF_ID, 128, 128) ^ (1ull << 62)); }
#define COPYN(d, s, n) _Pragma("unroll") for (int i_ = 0; i_ < (n); i_++) { uint32_t c_; asm volatile("mov.b32 %0, %1;" : "=r"(c_) : "f"((s)[i_])); (d)[i_] = __uint_as_float(c_); }
#define COPY64(d, s) COPYN(d, s, 64)
#define XM_DONE() { ACC_FENCE(T_, 64); COPY64(S1, T_); ACC_FENCE(S1, 64); \
      __syncwarp(); if (elect_one()) mbar_arrive_local(bar_lx); }
#define LOAD_X() { float T_[64]; ACC_DEF(T_, 64); wgmma_wait<0>(); XM_ISSUE(); wgmma_commit(); wgmma_wait<0>(); XM_DONE(); }

    float S0[96], S1[96];
#define FIRST_STEP(l_) { const int ln_ = (l_), l = ln_; const uint32_t ub = bar_full; (void)l; (void)ub; ACC_DEF(S0, 96); wgmma_fence(); wgmma4_n192<0>(S0, dA0 + (OFF_S >> 4), dB0); wgmma_commit(); PROFS(); }
    mbar_wait(bar_full, 0);
    FIRST_STEP(0);
    LOAD_EPOCH();
#pragma unroll 1
    for (int l = 0;; l++) {
      const uint32_t par = l & 1;
      uint32_t ub = bar_full + 8;
      PROF(1);
      {
        LANE_CONSTS();
        uint32_t ta[4];
#pragma unroll
        for (int j = 0; j < 4; j++) ta[j] = pK + srowoff + ((((uint32_t)j << 5) + lhi) ^ lsw);
        float p0, p1, a0 = 0.f, a1 = 0.f, q0 = 0.f, q1 = 0.f;
#define STATS(j0, j1) _Pragma("unroll") for (int j = (j0); j < (j1); j++) { \
          uint32_t x[4]; \
          ldsm_x4(ta[j & 3] + (j >> 2) * SLOT, x[0], x[1], x[2], x[3]); \
          if (j == 0) { p0 = __shfl_sync(0xffffffffu, bf_lo(x[0]), lane & 28); p1 = __shfl_sync(0xffffffffu, bf_lo(x[1]), lane & 28); } \
          _Pragma("unroll") for (int i = 0; i < 4; i += 2) { \
            const float d0 = bf_lo(x[i]) - p0, d1 = bf_hi(x[i]) - p0, d2 = bf_lo(x[i + 1]) - p1, d3 = bf_hi(x[i + 1]) - p1; \
            a0 += d0 + d1; a1 += d2 + d3; \
            q0 = fmaf(d1, d1, fmaf(d0, d0, q0)); q1 = fmaf(d3, d3, fmaf(d2, d2, q1)); } } \
          asm volatile("" : "+f"(a0), "+f"(a1), "+f"(q0), "+f"(q1), "+f"(p0), "+f"(p1)); SCHED_FENCE()
        if (SB0) { STATS(0, SB0); }
        bar_wg(wg);
        QSTEP(S0, dA0 + ((OFF_S + SLOT) >> 4), 1);
        QREL();
        SCHED_FENCE();
        STATS(SB0, SB1);
        ACC_DEF(S1, 96);
        QSTEP(S1, dA0 + (OFF_S >> 4), 0);
        QREL();
        SCHED_FENCE();
        STATS(SB1, SB2);
        QSTEP(S1, dA0 + ((OFF_S + SLOT) >> 4), 1);
        QREL();
        SCHED_FENCE();
        STATS(SB2, 8);
#pragma unroll
        for (int o = 1; o <= 2; o <<= 1) {
          a0 += __shfl_xor_sync(0xffffffffu, a0, o); a1 += __shfl_xor_sync(0xffffffffu, a1, o);
          q0 += __shfl_xor_sync(0xffffffffu, q0, o); q1 += __shfl_xor_sync(0xffffffffu, q1, o);
        }
        if (t == 1) { a0 = a1; q0 = q1; p0 = p1; }
        if (t < 2) st_b64(g_stats + (size_t)(mm * 128 + r0 + g + t * 8) * 8 + jj, __float_as_uint(fmaf(a0, 1.f / 128.f, p0)),
                          (__float_as_uint(fmaxf(fmaf(a0 * (-1.f / 128.f), a0, q0), 0.f)) & ~3u) | STAT_TAG(l));
        if (l) { asm volatile("cp.async.bulk.wait_group 0;" ::: "memory"); bar_arrive<BAR_X1, 288>(); }
#pragma unroll 1
        for (int i = 0; i < 14; i++) {
          QSTEP(S0, RA_CUR, 1);
          if (i == 0) PROF(2);
          QREL();
        }
      }
      LANE_CONSTS();
      mbar_wait(bar_stat, par);
      LNSTEP(S0, 0);
      wgmma_commit();
      const float rs0 = lds32f(sbase + OFF_ST + (r0 + g) * 4), rs1 = lds32f(sbase + OFF_ST + (r0 + g + 8) * 4);
      PUMP0();
      ACC_FENCE(S0, 96);
      PROF(3);
      if (!par) {
        constexpr uint32_t par = 0;
        uint32_t qa[16];
        uint32_t kf[24], vf[24];
#define DRAIN_A(ACC, hp, PMP) { \
          LANE_CONSTS(); \
          FRAG(kf, ACC + 32, 0, (hp) * 2); \
          PMP; \
          FRAG(vf, ACC + 64, 1, (hp) * 2 + 1); \
          _Pragma("unroll") for (int i_ = 0; i_ < 16; i_++) qa[i_] = pack_bf16(ACC[2 * i_], ACC[2 * i_ + 1]); \
          PINU(qa, 16); }
        DRAIN_A(S0, 0, PUMP0());
        if (l == 0 && NLAYERS > 1) {
#pragma unroll 1
          for (int rd = 1; rd >= 0; rd--) {
            FOLD(sbase + (12 - rd) * SLOT, rd);
            fence_proxy_async_smem();
            asm volatile("bar.arrive %0, 288;" :: "r"(BAR_WF + 1 - rd) : "memory");
          }
        }
        PUMPS(FPUMP);
        if (l == 0 && NLAYERS > 1) mbar_wait(bar_phi, 1);
#pragma unroll 1
        for (int h = 0; h < 2; h++) {
          PROFH(4, 16);
          LANE_CONSTS();
          FRAG_PUT(kf + 16, 10); FRAG_PUT(vf + 16, 11);
          STG_ARRIVE();
          if (h) { PROF(8); LOAD_X(); PROF(9); WSTEP(); PROF(10); } else PUMPS(HPUMP2);
          const bool gt0 = 2 * t > g, gt1 = 2 * t >= g;
          uint32_t msk[2] = {(gt0 ? 0xFFFFu : 0u) | (gt1 ? 0xFFFF0000u : 0u), g == 2 * t ? 0x10001u : 0u};
          PINU(msk, 2);
          TILE_CONSTS(sbase, false, 0);
          (void)pm0; (void)pbit;
          if (h) PROF(12);
          STG_WAIT();
          if (h) PROF(14);
          if (warp < 2) mbar_wait(bar_halo, h);
          if (h) PROF(15);
          FRAG_GET(kf, 10);
          PROFH(5, 17);
          float s[2][3][4];
#pragma unroll
          for (int ks = 0; ks < 2; ks++)
#pragma unroll
            for (int i = 0; i < 6; i++) {
              const int hh = i & 1, jb = 2 - (i >> 1);
              const uint32_t* b = kf + jb * 8 + hh * 4 + ks * 2;
              if (ks) mma_bf16(s[hh][jb], qa[hh * 8 + 4], qa[hh * 8 + 5], qa[hh * 8 + 6], qa[hh * 8 + 7], b[0], b[1]);
              else mma_bf16_z(s[hh][jb], qa[hh * 8], qa[hh * 8 + 1], qa[hh * 8 + 2], qa[hh * 8 + 3], b[0], b[1]);
            }
          PUMP();
          PROFH(6, 18);
          float va[2][2], vb[2][2], mx[2][2];
#pragma unroll
          for (int hh = 0; hh < 2; hh++) {
            va[hh][0] = gt0 ? s[hh][0][0] : s[hh][1][0];
            vb[hh][0] = gt1 ? s[hh][0][1] : s[hh][1][1];
            va[hh][1] = gt0 ? s[hh][1][2] : s[hh][2][2];
            vb[hh][1] = gt1 ? s[hh][1][3] : s[hh][2][3];
          }
          if (warp < 2 && mm == 0) {
#pragma unroll
            for (int hh = 0; hh < 2; hh++) { if (gt0) va[hh][0] = -INFINITY; if (gt1) vb[hh][0] = -INFINITY; }
          }
#pragma unroll
          for (int i = 0; i < 4; i++) mx[i >> 1][i & 1] = fmaxf(va[i >> 1][i & 1], vb[i >> 1][i & 1]);
#pragma unroll
          for (int o = 1; o <= 2; o <<= 1)
#pragma unroll
            for (int i = 0; i < 4; i++) mx[i >> 1][i & 1] = fmaxf(mx[i >> 1][i & 1], __shfl_xor_sync(0xffffffffu, mx[i >> 1][i & 1], o));
          const float sc0 = rs0 * (0.17677669529663687f * LOG2E), sc1 = rs1 * (0.17677669529663687f * LOG2E);
#pragma unroll
          for (int i = 0; i < 4; i++) {
            const float sc = (i & 1) ? sc1 : sc0, m = mx[i >> 1][i & 1];
            va[i >> 1][i & 1] = ex2((va[i >> 1][i & 1] - m) * sc); vb[i >> 1][i & 1] = ex2((vb[i >> 1][i & 1] - m) * sc);
            mx[i >> 1][i & 1] = va[i >> 1][i & 1] + vb[i >> 1][i & 1];
          }
          if (h == 0) { PIN(&va[0][0], 4); PIN(&vb[0][0], 4); PIN(&mx[0][0], 4); PUMP1(); }
          if (h) PROF(20);
          if (warp < 2) mbar_wait(bar_halo + 8, h);
          if (h) PROF(21);
          FRAG_GET(vf, 11);
#pragma unroll
          for (int o = 1; o <= 2; o <<= 1)
#pragma unroll
            for (int i = 0; i < 4; i++) mx[i >> 1][i & 1] += __shfl_xor_sync(0xffffffffu, mx[i >> 1][i & 1], o);
          float o[8][4];
          uint32_t pa[4][2];
#pragma unroll
          for (int i = 0; i < 4; i++) {
            const float iv = rcp_fast(mx[i >> 1][i & 1]);
            const uint32_t w = pack_bf16(va[i >> 1][i & 1] * iv, vb[i >> 1][i & 1] * iv);
            pa[i][0] = w & msk[0]; pa[i][1] = w & ~msk[0];
          }
          PROFH(7, 19);
#pragma unroll
          for (int i = 7; i >= 0; i--) {
            const uint32_t* a = vf + (i >> 2) * 8 + (i & 3) * 2;
            mma_bf16_z(o[i], a[0], a[1], a[8], a[9], pa[(i & 2) + (i >> 2)][0], pa[(i & 2) + (i >> 2)][1]);
          }
          if (h == 0) PUMP1() else mbar_wait(bar_done + 30 * 8, par);
          if (NLAYERS > 1) mbar_wait(bar_phi + 8, 0);
          if (h) PROF(22);
          {
            const uint32_t pm0 = msk[1], pbit = O_BIT(l) * 0x10001u;
#pragma unroll
            for (int i = 0; i < 4; i++)
              stsm_x4_t(ta[i] + (h ? 3 : 12) * SLOT, PBIT(pack_bf16(o[i][0], o[i][1])), PBIT(pack_bf16(o[i + 4][0], o[i + 4][1])),
                        pack_bf16(o[i][2], o[i][3]), pack_bf16(o[i + 4][2], o[i + 4][3]));
          }
          WARP_STORE(&tm_os, sbase + (h ? 3 : 12) * SLOT, jj * 128 + h * 64, mm * 128);
          PROFH(11, 23);
          if (h) break;
          REST_P1(ASKEW);
          asm volatile("cp.async.bulk.wait_group.read 0;" ::: "memory");
          DRAIN_A(S1, 1, {});
        }
      } else {
        constexpr uint32_t par = 1;
        float st[32];
        const float c0 = rs0 * LOG2E, c1 = rs1 * LOG2E;
        { V_ADDR(pV, 0); STAGE_V(S0 + 64); }
        if (warp < 2) sts128(sbase + OFF_ONES + warp * 512 + lane * 16, 0x3F803F80u, 0x3F803F80u, 0x3F803F80u, 0x3F803F80u);
        scale32(st, S0, c0, c1);
        PIN(st, 32);
#define PHI_PIECE(c) { \
          e_[2 * (c)] = ex2(st[2 * (c)]); e_[2 * (c) + 1] = ex2(st[2 * (c) + 1]); \
          _Pragma("unroll") for (int k_ = 4 * (c); k_ < 4 * (c) + 4; k_++) m_[(c) >> 1] = (k_ & 7) ? fmaf(st[k_], st[k_], m_[(c) >> 1]) : st[k_] * st[k_]; \
          asm volatile("" : "+f"(e_[2 * (c)]), "+f"(e_[2 * (c) + 1]), "+f"(m_[(c) >> 1])); SCHED_FENCE(); }
#define PHI_FIN() { \
          big = __any_sync(0xffffffffu, !(fmaxf(fmaxf(m_[0], m_[1]), fmaxf(m_[2], m_[3])) < BIGLIM)); \
          if (__builtin_expect(big, 0)) { COPYN(e_, st, 16); } \
          _Pragma("unroll") for (int k_ = 0; k_ < 16; k_++) st[k_] = e_[k_]; \
          PIN(st, 16); }
#define KV_MMA(vs, IL) { \
          const uint32_t dp = dA0 + 12 * 1024 - wg * 2560, dv = dA0 + (vs) * 1024 + ((OFF_ONES - (vs) * SLOT - 16) << 12) - wg * (512 << 16); \
          STG_WAIT(); \
          wgmma_fence(); \
          _Pragma("unroll") for (int ks = 0; ks < 8; ks++) { \
            const uint64_t a = DESC(dp + ks * 128, 0x40000040), b = DESC(dv + ks * (64 - (64 << 16)), 0x80000020); \
            if ((IL) && ks) wgmma_fence(); \
            if (ks == 0) wgmma_n40<0, 1>(kv, a, b); else wgmma_n40<1, 1>(kv, a, b); \
            if (ks == 7) wgmma_commit(); \
            if (IL) PHI_PIECE(ks); } }
#define KV_RED1(i) if (h) red_v4(g_kv[l >> 1] + (jj * 4) * KVH + warp * 768 + lane * 4 + (i) * 128, S0[32 + (i) * 3], S0[33 + (i) * 3], S0[34 + (i) * 3], 1.f)
#define KV_REDS(n) { _Pragma("unroll") for (int i_ = 0; i_ < 6; i_++) if (((RPACE >> (4 * i_)) & 15) == (n)) KV_RED1(i_); }
#define KV_SEND(kp) { \
          float sd[9]; \
          _Pragma("unroll") for (int i = 0; i < 8; i++) { (kp)[i] = kv[i]; sd[i] = kv[8 + i]; } \
          (kp)[8] = rank ? kv[18] : kv[16]; sd[8] = rank ? kv[16] : kv[18]; \
          const uint32_t ra = sbase + peer + (warp * 32 + lane) * 4, rb = bar_kx + peer; \
          if (elect_one()) mbar_expect_tx(bar_kx, 1152); \
          _Pragma("unroll") for (int i = 0; i < 2; i++) \
            asm volatile("st.async.weak.shared::cluster.mbarrier::complete_tx::bytes.v4.f32 [%0], {%1, %2, %3, %4}, [%5];" \
                         :: "r"(ra + (warp * 32 + lane) * 12 + OFF_PHI + i * 4096), "f"(sd[4 * i]), "f"(sd[4 * i + 1]), "f"(sd[4 * i + 2]), "f"(sd[4 * i + 3]), "r"(rb) : "memory"); \
          asm volatile("st.async.weak.shared::cluster.mbarrier::complete_tx::bytes.f32 [%0], %1, [%2];" :: "r"(ra + OFF_LNB), "f"(sd[8]), "r"(rb) : "memory"); }
#define KV_RECV(kp, hp) { \
          float r_[9]; \
          float* kvg = g_kv[l >> 1] + (jj * 4 + (hp) * 2) * KVH + warp * 768 + rank * 384 + lane * 4; \
          mbar_wait(bar_kx, l >> 1); \
          _Pragma("unroll") for (int i = 0; i < 2; i++) \
            asm volatile("ld.shared.v4.f32 {%0, %1, %2, %3}, [%4];" : "=f"(r_[4 * i]), "=f"(r_[4 * i + 1]), "=f"(r_[4 * i + 2]), "=f"(r_[4 * i + 3]) \
                         : "r"(sbase + OFF_PHI + i * 4096 + (warp * 32 + lane) * 16) : "memory"); \
          r_[8] = lds32f(sbase + OFF_LNB + (warp * 32 + lane) * 4); \
          _Pragma("unroll") for (int i = 0; i < 3; i++) red_v4(kvg + i * 128, (kp)[3 * i] + r_[3 * i], (kp)[3 * i + 1] + r_[3 * i + 1], (kp)[3 * i + 2] + r_[3 * i + 2], 2.f); }
#define KV_LOAD(hp) { \
          const uint4* kvg = reinterpret_cast<const uint4*>(g_kv[l >> 1] + (jj * 4 + (hp) * 2) * KVH) + warp * 192 + lane; \
          _Pragma("unroll") for (int i = 0; i < 6; i++) v[i] = ld_b128(kvg + i * 32); }
#define KVV(i) __uint_as_float((i) % 3 == 0 ? v[(i) / 3].x : ((i) % 3 == 1 ? v[(i) / 3].y : v[(i) / 3].z))
#define KV_TILE(hp) { \
          _Pragma("unroll 1") for (int it = 0; it < (1 << 16); it++) { \
            if (__all_sync(0xffffffffu, (v[0].w & v[1].w & v[2].w & v[3].w & v[4].w & v[5].w) == 0x41800000u)) break; \
            RETRY_COUNT(); \
            KV_LOAD(hp); \
          } \
          if (hp) PROF(26); else PROF(25); \
          const uint32_t e = lane & 7, jt = ((lane >> 1) & 4) + (e >> 1); \
          const uint32_t row = ((((warp >> 1) ^ wg) & 1) << 5) + ((jt & 1) << 4) + ((warp & 1) << 3) + (jt & 6) + (e & 1); \
          const uint32_t kd = pV + wg * 8192 + row * 128, ksw = (row & 7) << 4; \
          _Pragma("unroll") for (int i = 0; i < 2; i++) \
            stsm_x4(kd + ((i * 32 + lhi) ^ ksw), pack_bf16(KVV(i * 9), KVV(i * 9 + 1)), pack_bf16(KVV(i * 9 + 2), KVV(i * 9 + 3)), \
                    pack_bf16(KVV(i * 9 + 4), KVV(i * 9 + 5)), pack_bf16(KVV(i * 9 + 6), KVV(i * 9 + 7))); \
          stsm_x4(kd + ((64u + lhi) ^ ksw), pack_bf16(KVV(8), 1.f), pack_bf16(KVV(17), 1.f), 0u, 0u); }
#pragma unroll 1
        for (int h = 0; h < 2; h++) {
          PROFH(4, 6);
          PUMP0();
          LANE_CONSTS();
          const uint32_t dsw = (uint32_t)(g ^ (2 * t)) << 4, dst = ((t & 2) ? pK : sbase + 12 * SLOT) + (r0 + g) * 128;
          float e[16], f[16];
          KV_REDS(1);
          float sa = exps16_<0>(e, st);
          exps16_fix<0>(e, st, sa);
          asm volatile("" : "+f"(sa)); PIN(e, 16); PUMP0();
          if (h) STG_WAIT();
          KV_REDS(2);
          store16(e, sa, dst, dsw, 4);
          float sb = exps16_<1>(f, st);
          exps16_fix<1>(f, st, sb);
          asm volatile("" : "+f"(sb)); PIN(f, 16); PUMP0();
          KV_REDS(3);
          store16(f, sb, dst, dsw, 0);
          float sc = exps16_<0>(e, st + 2);
          exps16_fix<0>(e, st + 2, sc);
          asm volatile("" : "+f"(sc)); PIN(e, 16); PUMP0();
          KV_REDS(4);
          store16(e, sc, dst + 1024, dsw, 4);
          float sd = exps16_<1>(f, st + 2);
          exps16_fix<1>(f, st + 2, sd);
          asm volatile("" : "+f"(sd)); PIN(f, 16); PUMP0();
          store16(f, sd, dst + 1024, dsw, 0);
          PROFH(5, 7);
          if (h) break;
          {
            float kv[20];
            ACC_DEF(kv, 20);
            fence_proxy_async_smem();
            STG_ARRIVE();
            float e_[16], m_[4];
            KV_MMA(11, 0);
            PUMP0();
            ACC_FENCE(kv, 20);
            STG_ARRIVE();
            scale32(st, S0 + 32, c0, c1);
            PIN(st, 32);
            {
              COPYN(S0 + 32, kv, 8); COPYN(S0 + 40, kv + 16, 1); COPYN(S0 + 41, kv + 8, 8); COPYN(S0 + 49, kv + 18, 1);
              const int h = 1;
              KV_REDS(0);
            }
          }
        }
        bool big;
        uint4 v[6];
        {
          float kv[20];
          { LANE_CONSTS(); KV_LOAD(0); }
          mbar_wait(bar_stat2, par);
          LNSTEP(S1, 1);
          ub = bar_full + 240;
          PUMP1();
          if (wg == 0) bar_sync<BAR_SKEW, 256>();
          QSTEP(S1, RA_CUR, 1);
          if (wg == 1) bar_arrive<BAR_SKEW, 256>();
          QREL();
          { LANE_CONSTS(); KV_TILE(0); }
          LANE_CONSTS();
          V_ADDR(sbase + 3 * SLOT, rank * 32);
          PINU(va_, 2);
          mbar_wait(bar_done + 30 * 8, par);
          wgmma_wait<0>();
          ACC_FENCE(S1, 96);
          PROF(13);
          STAGE_V(S1 + 64);
          fence_proxy_async_smem();
          STG_ARRIVE();
          REL(bar_done + 31 * 8);
          scale32(st, S1, c0, c1);
          PIN(st, 32);
          PROF(16);
          ACC_DEF(kv, 20);
          float e_[16], m_[4];
          KV_MMA(3, 1);
          SCHED_FENCE();
          PROF(14);
          PHI_FIN();
          SCHED_FENCE();
          PROF(15);
          wgmma_wait<0>();
          ACC_FENCE(kv, 20);
          PROF(12);
          { float kp[9]; KV_SEND(kp); _Pragma("unroll") for (int i = 0; i < 3; i++) v[i] = make_uint4(__float_as_uint(kp[3 * i]), __float_as_uint(kp[3 * i + 1]), __float_as_uint(kp[3 * i + 2]), 0u); }
          PROF(17);
        }
#pragma unroll 1
        for (int h = 0; h < 2; h++) {
          const uint32_t pO = sbase + (h ? 3 : 8) * SLOT;
          LANE_CONSTS();
          uint32_t fq[32];
          PROFH(18, 32);
          SCHED_FENCE();
          phiq_b<1>(fq, st, big); PINU(fq, 16); PIN(st + 16, 16);
          SCHED_FENCE();
          PROFH(8, 9);
          if (h) {
            asm volatile("cp.async.bulk.wait_group.read 0;" ::: "memory");
            mbar_wait(bar_lx, par);
            PROF(30);
            KV_TILE(1);
            fence_proxy_async_smem();
            STG_ARRIVE();
          }
          SCHED_FENCE();
          if (h == 0) {
            float kp[9];
#pragma unroll
            for (int i = 0; i < 9; i++) kp[i] = KVV(i);
            KV_RECV(kp, 1);
            SCHED_FENCE();
          }
          phiq_b<0>(fq + 16, st + 16, big); PINU(fq + 16, 16);
          PROFH(10, 21);
          if (h) STG_WAIT();
          wgmma_wait<0>();
          ACC_FENCE(S1, 64);
          PROFH(19, 33);
          float o[4][20];
#define O_MMA(hh) { \
            const uint64_t db = make_desc(pV + (hh) * 8192, 16, 1024); \
            ACC_DEF(o[(hh) * 2], 20); ACC_DEF(o[(hh) * 2 + 1], 20); \
            wgmma_fence(); \
            wgmma_n40_rs<0>(o[(hh) * 2], fq + (hh) * 16, db + 256); wgmma_n40_rs<0>(o[(hh) * 2 + 1], fq + (hh) * 16 + 8, db); \
            wgmma_n40_rs<1>(o[(hh) * 2], fq + (hh) * 16 + 4, db + 384); wgmma_n40_rs<1>(o[(hh) * 2 + 1], fq + (hh) * 16 + 12, db + 128); \
            wgmma_commit(); }
          O_MMA(0);
          SCHED_FENCE();
          PMASKS(true, O_BIT(l));
#pragma unroll
          for (int hh = 0; hh < 2; hh++) {
            wgmma_wait<0>();
            ACC_FENCE(o[hh * 2], 20); ACC_FENCE(o[hh * 2 + 1], 20);
            if (!hh) { O_MMA(1); SCHED_FENCE(); }
            if (hh) PROFH(22, 24);
            const float* x = o[hh * 2];
            const float* y = o[hh * 2 + 1];
            const float sx0 = x[17] * 0x1p-40f, sy0 = y[17] * 0x1p-40f, sx1 = x[19] * 0x1p-40f, sy1 = y[19] * 0x1p-40f;
            const float i0 = rcp_fast(fmaf(fmaf(x[17], 1e-6f, x[16]), sy0, y[16] * sx0)), i1 = rcp_fast(fmaf(fmaf(x[19], 1e-6f, x[18]), sy1, y[18] * sx1));
            const float ax0 = sy0 * i0, ay0 = sx0 * i0, ax1 = sy1 * i1, ay1 = sx1 * i1;
#pragma unroll
            for (int dp = 0; dp < 2; dp++)
              stsm_x4(pO + srowoff + ((hh * 64 + dp * 32 + lhi) ^ lsw),
                      PBIT(pack_bf16(fmaf(x[dp * 8], ax0, y[dp * 8] * ay0), fmaf(x[dp * 8 + 1], ax0, y[dp * 8 + 1] * ay0))),
                      PBIT(pack_bf16(fmaf(x[dp * 8 + 2], ax1, y[dp * 8 + 2] * ay1), fmaf(x[dp * 8 + 3], ax1, y[dp * 8 + 3] * ay1))),
                      (pack_bf16(fmaf(x[dp * 8 + 4], ax0, y[dp * 8 + 4] * ay0), fmaf(x[dp * 8 + 5], ax0, y[dp * 8 + 5] * ay0))),
                      (pack_bf16(fmaf(x[dp * 8 + 6], ax1, y[dp * 8 + 6] * ay1), fmaf(x[dp * 8 + 7], ax1, y[dp * 8 + 7] * ay1))));
          }
          WARP_STORE(&tm_os, pO, jj * 128 + h * 64, mm * 128);
          PROFH(20, 34);
          if (h) break;
          float T_[64];
          scale32(st, S1 + 32, c0, c1);
          PIN(st, 32);
          ACC_DEF(T_, 64);
          XM_ISSUE(); wgmma_commit();
          SCHED_FENCE();
          big = any_big(st);
          SCHED_FENCE();
          PROF(27);
          wgmma_wait<0>(); XM_DONE();
          PROF(28);
          bar_wg(wg);
          WSTEP();
          SCHED_FENCE();
          PROF(29);
          KV_LOAD(1);
          phiq_a(st, big); PIN(st, 16);
          PROF(31);
        }
      }
      __syncwarp();
      if (elect_one()) mbar_arrive_local(bar_epi);
      bar_wg(wg);
#pragma unroll 1
      while (ub < bar_full + 384) {
        WSTEP();
        if (ub == bar_full + 8 * 41) { asm volatile("cp.async.bulk.wait_group.read 0;" ::: "memory"); PROF(35); }
        if (ub == bar_full + 8 * 42) PROF(36);
      }
      {
        float Wb[32];
        LANE_CONSTS();
        TILE_CONSTS(pK, l < NLAYERS - 1, X_BIT(l));
        if (l < NLAYERS - 1) mbar_wait(bar_full, par ^ 1);
        wgmma_wait<0>();
        ACC_FENCE(S1, 64);
        COPYN(Wb, S1 + 32, 32);
        PROF(37);
        X_OUT(0, S1);
        WARP_STORE(l < NLAYERS - 1 ? &tm_os : &tm_xo, pK, jj * 128 + (l < NLAYERS - 1 ? 0 : (warp & 1) * 1024), l < NLAYERS - 1 ? mm * 128 + S_LEN : mm * 64 + (warp >> 1) * 16 - r0);
        if (l == NLAYERS - 1) { PMASKS(false, 0); X_OUT(1, Wb); break; }
        PROF(38);
        bar_wg(wg);
        FIRST_STEP(l + 1);
        REL(bar_done + 47 * 8);
        PROF(39);
        { PMASKS(false, 0); X_OUT(1, Wb); }
        fence_proxy_async_smem();
      }
    }
    WARP_STORE(&tm_xo, pV, jj * 128 + 64 + (warp & 1) * 1024, mm * 64 + (warp >> 1) * 16 - r0);
    asm volatile("cp.async.bulk.wait_group.read 0;" ::: "memory");
    cluster_sync();
  }
}

typedef CUresult (*PFN_encode)(CUtensorMap*, CUtensorMapDataType, cuuint32_t, void*, const cuuint64_t*, const cuuint64_t*,
                               const cuuint32_t*, const cuuint32_t*, CUtensorMapInterleave, CUtensorMapSwizzle,
                               CUtensorMapL2promotion, CUtensorMapFloatOOBfill);

CUtensorMap make_map(PFN_encode enc, const void* ptr, uint64_t inner, uint64_t outer, uint32_t box_inner, uint32_t box_outer,
                     CUtensorMapSwizzle swz = CU_TENSOR_MAP_SWIZZLE_128B, int promo = CU_TENSOR_MAP_L2_PROMOTION_L2_256B) {
  CUtensorMap m;
  cuuint64_t dims[2] = {inner, outer};
  cuuint64_t strides[1] = {inner * 2};
  cuuint32_t box[2] = {box_inner, box_outer};
  cuuint32_t es[2] = {1, 1};
  enc(&m, CU_TENSOR_MAP_DATA_TYPE_BFLOAT16, 2, const_cast<void*>(ptr), dims, strides, box, es, CU_TENSOR_MAP_INTERLEAVE_NONE,
      swz, (CUtensorMapL2promotion)promo, CU_TENSOR_MAP_FLOAT_OOB_FILL_NONE);
  return m;
}

CUtensorMap make_tile_map(PFN_encode enc, const void* ptr, uint64_t rows, bool by_parity, int promo) {
  CUtensorMap m;
  cuuint64_t dims[4] = {D_MODEL, 16, 2, rows / 32};
  cuuint64_t strides[3] = {by_parity ? 4096u : 2048u, by_parity ? 2048u : 32768u, 65536};
  cuuint32_t box[4] = {64, 16, 2, 4};
  cuuint32_t es[4] = {1, 1, 1, 1};
  enc(&m, CU_TENSOR_MAP_DATA_TYPE_BFLOAT16, 4, const_cast<void*>(ptr), dims, strides, box, es, CU_TENSOR_MAP_INTERLEAVE_NONE,
      CU_TENSOR_MAP_SWIZZLE_128B, (CUtensorMapL2promotion)promo, CU_TENSOR_MAP_FLOAT_OOB_FILL_NONE);
  return m;
}

}

extern "C" void kernel_launch(void* const* d_in, const int* in_sizes, int n_in, void* d_out, int out_size) {
  (void)in_sizes; (void)n_in; (void)out_size;
  static PFN_encode enc = nullptr;
  if (!enc) {
    void* fn = nullptr;
    cudaDriverEntryPointQueryResult qr;
    cudaGetDriverEntryPoint("cuTensorMapEncodeTiled", &fn, cudaEnableDefault, &qr);
    enc = (PFN_encode)fn;
    cudaFuncSetAttribute(mega_kernel, cudaFuncAttributeMaxDynamicSharedMemorySize, SMEM_BYTES);
  }
  Params prm;
  prm.x0 = (const __nv_bfloat16*)d_in[0];
  prm.wA_qkv = (const __nv_bfloat16*)d_in[1];
  prm.wA_o = (const __nv_bfloat16*)d_in[2];
  prm.wB_qkv = (const __nv_bfloat16*)d_in[4];
  prm.wB_phi = (const __nv_bfloat16*)d_in[5];
  prm.wB_o = (const __nv_bfloat16*)d_in[6];
  prm.out = (__nv_bfloat16*)d_out;
  void *obuf = nullptr, *wf = nullptr;
  cudaGetSymbolAddress(&obuf, g_obuf);
  cudaGetSymbolAddress(&wf, g_wfold);
  CUtensorMap tm_x0 = make_tile_map(enc, d_in[0], S_LEN, true, XPROMO);
  CUtensorMap tm_xo = make_map(enc, d_out, 2 * D_MODEL, S_LEN / 2, 64, 16);
  CUtensorMap tm_os = make_map(enc, obuf, D_MODEL, 2 * S_LEN, 64, 16);
  CUtensorMap tm_o = make_tile_map(enc, obuf, 2 * S_LEN, false, OPROMO);
  CUtensorMap tm_wf = make_map(enc, wf, 2048, D_MODEL, 64, 32);
  CUtensorMap tm_wqA = make_map(enc, d_in[1], 3 * D_MODEL, D_MODEL, 64, 32, CU_TENSOR_MAP_SWIZZLE_128B, WPROMO);
  CUtensorMap tm_wqB = make_map(enc, prm.wB_qkv, 3 * D_MODEL, D_MODEL, 64, 32);
  CUtensorMap tm_woA = make_map(enc, prm.wA_o, D_MODEL, D_MODEL, 64, 64);
  CUtensorMap tm_woB = make_map(enc, prm.wB_o, D_MODEL, D_MODEL, 64, 64);
  CUtensorMap tm_phi = make_map(enc, prm.wB_phi, 32, 1024, 32, 128, CU_TENSOR_MAP_SWIZZLE_64B);
  mega_kernel<<<NMAIN + NAUX, 384, SMEM_BYTES>>>(tm_x0, tm_xo, tm_os, tm_o, tm_wf, tm_wqA, tm_wqB, tm_woA, tm_woB, tm_phi, prm);
}
```

```cpp
#include <cuda_runtime.h>
#include <cuda.h>
#include <cuda_bf16.h>
#include <stdint.h>

#define NLAYERS 4

#define HPUMP2 1
#define ASKEW 2
#define FPUMP 3
#define PFGAP 100
#define POLLGAP 120
#define HW1 29
#define XPACE 0x06050401000000ull
#define XP0 4
#define HW0 18
#define XD 4
#define WFGAP 50
#define EARLY 2
#define BIGLIM 3600.f
#define SUMLO 0x1p-100f
#define SUMHI 0x1p100f
#define XPROMO 2
#define OPROMO 3
#define STAG2 300
#define WPROMO 3
#define SB0 2
#define SB1 4
#define SB2 6
#define PROWS 3
#define SPD0 0
#define SPD1 0
#define SPD2 300
#define FRB 0x3535353535ull
#define NOB 0xFFFFFF00u
#define NO1 ~0u
#define NOX ~0u
#define FD0 0
#define FD1 3
#define RPACE 0x221100
namespace {

constexpr int S_LEN = 2048, D_MODEL = 1024;
constexpr int NAUX = 4, NMAIN = 128;
constexpr int SLOT = 16384;
constexpr int QST = 24576;
constexpr int OFF_RA = 6 * SLOT, OFF_S = 10 * SLOT;
constexpr int OFF_HALO = 13 * SLOT, OFF_LNB = OFF_HALO  , OFF_ONES = OFF_HALO + 3072;
constexpr int OFF_ST = OFF_HALO + 7168  , OFF_ID = OFF_HALO + 7680, OFF_PHI = OFF_HALO + 8192;
constexpr int OFF_BAR = 14 * SLOT;
constexpr int OFF_LNA = OFF_BAR + 1024;
constexpr int SMEM_BYTES = OFF_LNA + 2048;
#define WO_ASLOT(par) ((par) ? 0x9876CAB39876CA98ull : 0x98C76BA398C7698Cull)
constexpr unsigned long long WO_BSLOT = 0x5432105421054210ull;
__device__ __forceinline__ int srcb(int j, int i) { return (i + (i >= j)) & 7; }
__device__ __forceinline__ int kslice(int j, int i) { return i < 2 ? 2 * j + i : (i < 9 ? 2 * srcb(j, i - 2) : 2 * srcb(j, i - 9) + 1); }
__device__ __forceinline__ int wslice(int j, int s) { return 2 * ((s & 7) ? srcb(j, (s & 7) - 1) : j) + (s >> 3); }
constexpr int KVH = 6 * 128 * 4;

struct __align__(128) Flag { unsigned v; unsigned pad[31]; };
struct Flags {
  Flag xready[4][16];
  Flag wfready[8];
  Flag done;
  Flag epoch;
};

__device__ Flags g_flags;
__device__ __nv_bfloat16 g_obuf[2 * S_LEN * D_MODEL];
#define O_BIT(l) ((epoch * NLAYERS + (l) + 1) & 1u)
#define X_BIT(l) ((epoch * (NLAYERS - 1) + (l) + 1) & 1u)
__device__ __nv_bfloat16 g_wfold[D_MODEL * 2048];
__device__ uint4 g_halo[16 * 8 * 512];
__device__ __align__(128) float g_kv[2][32 * KVH];
__device__ __align__(128) uint2 g_colsum[2][1536][2];
__device__ __align__(128) uint2 g_stats[S_LEN * 8];
#define H_BIT(l) (NLAYERS > 2 ? (uint32_t)((l) == 0) : (ep1 & 1))
#define STAT_TAG(l) ((ep1 * NLAYERS + (l) + 1) & 3u)

#define RETRY_COUNT()
#define PRL 0
#define PRU 0
#define PROFL 1
#define PROFW 0
#define PROFT(i) do {} while (0)
#define PROF(i) do {} while (0)
#define PROFH(i, j) do {} while (0)

__device__ __forceinline__ uint32_t smem_u32(const void* p) { return (uint32_t)__cvta_generic_to_shared(p); }
__device__ __forceinline__ bool elect_one() {
  uint32_t p;
  asm volatile("{\n.reg .pred p;\nelect.sync _|p, 0xffffffff;\nselp.u32 %0, 1, 0, p;\n}\n" : "=r"(p));
  return p != 0;
}
__device__ __forceinline__ void mbar_init(uint32_t bar, uint32_t cnt) {
  asm volatile("mbarrier.init.shared::cta.b64 [%0], %1;" :: "r"(bar), "r"(cnt));
}
__device__ __forceinline__ void mbar_expect_tx(uint32_t bar, uint32_t bytes) {
  asm volatile("mbarrier.arrive.expect_tx.shared::cta.b64 _, [%0], %1;" :: "r"(bar), "r"(bytes) : "memory");
}
#define mbar_wait(bar, parity) \
  asm volatile("{\n.reg .pred p, q;\nW_%=:\nmbarrier.try_wait.parity.shared::cta.b64 p, [%1], %2;\nadd.s32 %0, %0, -1;\n" \
               "setp.gt.and.s32 q, %0, 0, !p;\n@q bra.uni W_%=;\n}\n" : "+r"(budget) : "r"((uint32_t)(bar)), "r"((uint32_t)(parity)) : "memory")
#define mbar_wait_sl(bar, parity) \
  asm volatile("{\n.reg .pred p, q;\nW_%=:\nmbarrier.try_wait.parity.shared::cta.b64 p, [%1], %2, 20000;\nadd.s32 %0, %0, -64;\n" \
               "setp.gt.and.s32 q, %0, 0, !p;\n@q bra.uni W_%=;\n}\n" : "+r"(budget) : "r"((uint32_t)(bar)), "r"((uint32_t)(parity)) : "memory")
__device__ __forceinline__ void mbar_arrive_local(uint32_t bar) {
  asm volatile("mbarrier.arrive.shared::cta.b64 _, [%0];" :: "r"(bar) : "memory");
}
__device__ __forceinline__ void tma_load_2d(uint32_t dst, const CUtensorMap* tm, uint32_t bar, int c0, int c1) {
  asm volatile("cp.async.bulk.tensor.2d.shared::cluster.global.mbarrier::complete_tx::bytes [%0], [%1, {%3, %4}], [%2];"
               :: "r"(dst), "l"(tm), "r"(bar), "r"(c0), "r"(c1) : "memory");
}
__device__ __forceinline__ void tma_load_2d_mc(uint32_t dst, const CUtensorMap* tm, uint32_t bar, int c0, int c1) {
  asm volatile("cp.async.bulk.tensor.2d.shared::cluster.global.mbarrier::complete_tx::bytes.multicast::cluster [%0], [%1, {%3, %4}], [%2], %5;"
               :: "r"(dst), "l"(tm), "r"(bar), "r"(c0), "r"(c1), "h"((uint16_t)3) : "memory");
}
__device__ __forceinline__ void tma_store_2d(const CUtensorMap* tm, uint32_t src, int c0, int c1) {
  asm volatile("cp.async.bulk.tensor.2d.global.shared::cta.bulk_group [%0, {%2, %3}], [%1];"
               :: "l"(tm), "r"(src), "r"(c0), "r"(c1) : "memory");
}
__device__ __forceinline__ void tma_load_t(uint32_t dst, const CUtensorMap* tm, uint32_t bar, int c0, int row) {
  asm volatile("cp.async.bulk.tensor.4d.shared::cluster.global.mbarrier::complete_tx::bytes [%0], [%1, {%3, %5, %5, %4}], [%2];"
               :: "r"(dst), "l"(tm), "r"(bar), "r"(c0), "r"(row >> 5), "r"(0) : "memory");
}
__device__ __forceinline__ void tma_store_t(const CUtensorMap* tm, uint32_t src, int c0, int row) {
  asm volatile("cp.async.bulk.tensor.4d.global.shared::cta.bulk_group [%0, {%2, %4, %4, %3}], [%1];"
               :: "l"(tm), "r"(src), "r"(c0), "r"(row >> 5), "r"(0) : "memory");
}
__device__ __forceinline__ void bulk_commit_wait() {
  asm volatile("cp.async.bulk.commit_group;\ncp.async.bulk.wait_group 0;" ::: "memory");
}
__device__ __forceinline__ void prefetch_tmap(const CUtensorMap* tm) {
  asm volatile("prefetch.tensormap [%0];" :: "l"(tm) : "memory");
}
__device__ __forceinline__ void fence_proxy_async_global() { asm volatile("fence.proxy.async.global;" ::: "memory"); }
__device__ __forceinline__ void fence_proxy_async_smem() { asm volatile("fence.proxy.async.shared::cta;" ::: "memory"); }
__device__ __forceinline__ unsigned ld_relaxed(const unsigned* p) {
  unsigned v;
  asm volatile("ld.relaxed.gpu.global.u32 %0, [%1];" : "=r"(v) : "l"(p) : "memory");
  return v;
}
__device__ __forceinline__ void fence_acquire() { asm volatile("fence.acquire.gpu;" ::: "memory"); }
__device__ __forceinline__ void wait_flag(const unsigned* p, unsigned target) {
  int it = 0;
  while ((int)(ld_relaxed(p) - target) < 0 && ++it < (1 << 20)) {}
  fence_acquire();
}
__device__ __forceinline__ void signal_release(unsigned* p) {
  asm volatile("red.release.gpu.global.add.u32 [%0], 1;" :: "l"(p) : "memory");
}
template <int ID, int N> __device__ __forceinline__ void bar_arrive() { asm volatile("bar.arrive %0, %1;" :: "n"(ID), "n"(N) : "memory"); }
template <int ID, int N> __device__ __forceinline__ void bar_sync() { asm volatile("bar.sync %0, %1;" :: "n"(ID), "n"(N) : "memory"); }
__device__ __forceinline__ void bar_wg(int wg) { asm volatile("bar.sync %0, 128;" :: "r"(2 + wg) : "memory"); }
__device__ __forceinline__ void cluster_sync() {
  asm volatile("barrier.cluster.arrive.relaxed.aligned;\nbarrier.cluster.wait.aligned;" ::: "memory");
}
__device__ __forceinline__ void cluster_wait() { asm volatile("barrier.cluster.wait.acquire.aligned;" ::: "memory"); }
enum { BAR_X1 = 7, BAR_WF = 8  , BAR_SKEW = 10 };

__device__ __forceinline__ void wgmma_fence() { asm volatile("wgmma.fence.sync.aligned;" ::: "memory"); }
__device__ __forceinline__ void wgmma_commit() { asm volatile("wgmma.commit_group.sync.aligned;" ::: "memory"); }
template <int N> __device__ __forceinline__ void wgmma_wait() { asm volatile("wgmma.wait_group.sync.aligned %0;" :: "n"(N) : "memory"); }

template <int scale_d, int tnsp_b = 1> __device__ __forceinline__ void wgmma_n192(float* d, uint64_t descA, uint64_t descB) {
  asm volatile("{\n.reg .pred p;\nsetp.ne.b32 p, %98, 0;\n"
               "wgmma.mma_async.sync.aligned.m64n192k16.f32.bf16.bf16 {%0,%1,%2,%3,%4,%5,%6,%7,%8,%9,%10,%11,%12,%13,%14,%15,%16,%17,%18,%19,%20,%21,%22,%23,%24,%25,%26,%27,%28,%29,%30,%31,%32,%33,%34,%35,%36,%37,%38,%39,%40,%41,%42,%43,%44,%45,%46,%47,%48,%49,%50,%51,%52,%53,%54,%55,%56,%57,%58,%59,%60,%61,%62,%63,%64,%65,%66,%67,%68,%69,%70,%71,%72,%73,%74,%75,%76,%77,%78,%79,%80,%81,%82,%83,%84,%85,%86,%87,%88,%89,%90,%91,%92,%93,%94,%95}, %96, %97, p, 1, 1, 0, %99;\n}\n"
               : "+f"(d[0]), "+f"(d[1]), "+f"(d[2]), "+f"(d[3]), "+f"(d[4]), "+f"(d[5]), "+f"(d[6]), "+f"(d[7]), "+f"(d[8]), "+f"(d[9]), "+f"(d[10]), "+f"(d[11]), "+f"(d[12]), "+f"(d[13]), "+f"(d[14]), "+f"(d[15]), "+f"(d[16]), "+f"(d[17]), "+f"(d[18]), "+f"(d[19]), "+f"(d[20]), "+f"(d[21]), "+f"(d[22]), "+f"(d[23]), "+f"(d[24]), "+f"(d[25]), "+f"(d[26]), "+f"(d[27]), "+f"(d[28]), "+f"(d[29]), "+f"(d[30]), "+f"(d[31]), "+f"(d[32]), "+f"(d[33]), "+f"(d[34]), "+f"(d[35]), "+f"(d[36]), "+f"(d[37]), "+f"(d[38]), "+f"(d[39]), "+f"(d[40]), "+f"(d[41]), "+f"(d[42]), "+f"(d[43]), "+f"(d[44]), "+f"(d[45]), "+f"(d[46]), "+f"(d[47]), "+f"(d[48]), "+f"(d[49]), "+f"(d[50]), "+f"(d[51]), "+f"(d[52]), "+f"(d[53]), "+f"(d[54]), "+f"(d[55]), "+f"(d[56]), "+f"(d[57]), "+f"(d[58]), "+f"(d[59]), "+f"(d[60]), "+f"(d[61]), "+f"(d[62]), "+f"(d[63]), "+f"(d[64]), "+f"(d[65]), "+f"(d[66]), "+f"(d[67]), "+f"(d[68]), "+f"(d[69]), "+f"(d[70]), "+f"(d[71]), "+f"(d[72]), "+f"(d[73]), "+f"(d[74]), "+f"(d[75]), "+f"(d[76]), "+f"(d[77]), "+f"(d[78]), "+f"(d[79]), "+f"(d[80]), "+f"(d[81]), "+f"(d[82]), "+f"(d[83]), "+f"(d[84]), "+f"(d[85]), "+f"(d[86]), "+f"(d[87]), "+f"(d[88]), "+f"(d[89]), "+f"(d[90]), "+f"(d[91]), "+f"(d[92]), "+f"(d[93]), "+f"(d[94]), "+f"(d[95])
               : "l"(descA), "l"(descB), "n"(scale_d), "n"(tnsp_b));
}
template <int scale_d> __device__ __forceinline__ void wgmma4_n192(float* d, uint32_t da, uint32_t db) {
#define R_ "{%0,%1,%2,%3,%4,%5,%6,%7,%8,%9,%10,%11,%12,%13,%14,%15,%16,%17,%18,%19,%20,%21,%22,%23,%24,%25,%26,%27,%28,%29,%30,%31,%32,%33,%34,%35,%36,%37,%38,%39,%40,%41,%42,%43,%44,%45,%46,%47,%48,%49,%50,%51,%52,%53,%54,%55,%56,%57,%58,%59,%60,%61,%62,%63,%64,%65,%66,%67,%68,%69,%70,%71,%72,%73,%74,%75,%76,%77,%78,%79,%80,%81,%82,%83,%84,%85,%86,%87,%88,%89,%90,%91,%92,%93,%94,%95}"
  asm volatile("{\n.reg .pred p, q;\n.reg .b64 a, b;\nsetp.ne.b32 p, %98, 0;\nsetp.eq.b32 q, 0, 0;\nmov.b64 a, {%96, 0x40000040};\nmov.b64 b, {%97, 0x40000040};\n"
               "wgmma.mma_async.sync.aligned.m64n192k16.f32.bf16.bf16 " R_ ", a, b, p, 1, 1, 0, 1;\nadd.s64 a, a, 2;\nadd.s64 b, b, 128;\n"
               "wgmma.mma_async.sync.aligned.m64n192k16.f32.bf16.bf16 " R_ ", a, b, q, 1, 1, 0, 1;\nadd.s64 a, a, 2;\nadd.s64 b, b, 128;\n"
               "wgmma.mma_async.sync.aligned.m64n192k16.f32.bf16.bf16 " R_ ", a, b, q, 1, 1, 0, 1;\nadd.s64 a, a, 2;\nadd.s64 b, b, 128;\n"
               "wgmma.mma_async.sync.aligned.m64n192k16.f32.bf16.bf16 " R_ ", a, b, q, 1, 1, 0, 1;\n}\n"
               : "+f"(d[0]), "+f"(d[1]), "+f"(d[2]), "+f"(d[3]), "+f"(d[4]), "+f"(d[5]), "+f"(d[6]), "+f"(d[7]), "+f"(d[8]), "+f"(d[9]), "+f"(d[10]), "+f"(d[11]), "+f"(d[12]), "+f"(d[13]), "+f"(d[14]), "+f"(d[15]), "+f"(d[16]), "+f"(d[17]), "+f"(d[18]), "+f"(d[19]), "+f"(d[20]), "+f"(d[21]), "+f"(d[22]), "+f"(d[23]), "+f"(d[24]), "+f"(d[25]), "+f"(d[26]), "+f"(d[27]), "+f"(d[28]), "+f"(d[29]), "+f"(d[30]), "+f"(d[31]), "+f"(d[32]), "+f"(d[33]), "+f"(d[34]), "+f"(d[35]), "+f"(d[36]), "+f"(d[37]), "+f"(d[38]), "+f"(d[39]), "+f"(d[40]), "+f"(d[41]), "+f"(d[42]), "+f"(d[43]), "+f"(d[44]), "+f"(d[45]), "+f"(d[46]), "+f"(d[47]), "+f"(d[48]), "+f"(d[49]), "+f"(d[50]), "+f"(d[51]), "+f"(d[52]), "+f"(d[53]), "+f"(d[54]), "+f"(d[55]), "+f"(d[56]), "+f"(d[57]), "+f"(d[58]), "+f"(d[59]), "+f"(d[60]), "+f"(d[61]), "+f"(d[62]), "+f"(d[63]), "+f"(d[64]), "+f"(d[65]), "+f"(d[66]), "+f"(d[67]), "+f"(d[68]), "+f"(d[69]), "+f"(d[70]), "+f"(d[71]), "+f"(d[72]), "+f"(d[73]), "+f"(d[74]), "+f"(d[75]), "+f"(d[76]), "+f"(d[77]), "+f"(d[78]), "+f"(d[79]), "+f"(d[80]), "+f"(d[81]), "+f"(d[82]), "+f"(d[83]), "+f"(d[84]), "+f"(d[85]), "+f"(d[86]), "+f"(d[87]), "+f"(d[88]), "+f"(d[89]), "+f"(d[90]), "+f"(d[91]), "+f"(d[92]), "+f"(d[93]), "+f"(d[94]), "+f"(d[95])
               : "r"(da), "r"(db), "n"(scale_d));
#undef R_
}
template <int scale_d> __device__ __forceinline__ void wgmma4_n128(float* d, uint32_t da, uint32_t db) {
#define R_ "{%0,%1,%2,%3,%4,%5,%6,%7,%8,%9,%10,%11,%12,%13,%14,%15,%16,%17,%18,%19,%20,%21,%22,%23,%24,%25,%26,%27,%28,%29,%30,%31,%32,%33,%34,%35,%36,%37,%38,%39,%40,%41,%42,%43,%44,%45,%46,%47,%48,%49,%50,%51,%52,%53,%54,%55,%56,%57,%58,%59,%60,%61,%62,%63}"
  asm volatile("{\n.reg .pred p, q;\n.reg .b64 a, b;\nsetp.ne.b32 p, %66, 0;\nsetp.eq.b32 q, 0, 0;\nmov.b64 a, {%64, 0x40000040};\nmov.b64 b, {%65, 0x40000040};\n"
               "wgmma.mma_async.sync.aligned.m64n128k16.f32.bf16.bf16 " R_ ", a, b, p, 1, 1, 0, 1;\nadd.s64 a, a, 2;\nadd.s64 b, b, 128;\n"
               "wgmma.mma_async.sync.aligned.m64n128k16.f32.bf16.bf16 " R_ ", a, b, q, 1, 1, 0, 1;\nadd.s64 a, a, 2;\nadd.s64 b, b, 128;\n"
               "wgmma.mma_async.sync.aligned.m64n128k16.f32.bf16.bf16 " R_ ", a, b, q, 1, 1, 0, 1;\nadd.s64 a, a, 2;\nadd.s64 b, b, 128;\n"
               "wgmma.mma_async.sync.aligned.m64n128k16.f32.bf16.bf16 " R_ ", a, b, q, 1, 1, 0, 1;\n}\n"
               : "+f"(d[0]), "+f"(d[1]), "+f"(d[2]), "+f"(d[3]), "+f"(d[4]), "+f"(d[5]), "+f"(d[6]), "+f"(d[7]), "+f"(d[8]), "+f"(d[9]), "+f"(d[10]), "+f"(d[11]), "+f"(d[12]), "+f"(d[13]), "+f"(d[14]), "+f"(d[15]), "+f"(d[16]), "+f"(d[17]), "+f"(d[18]), "+f"(d[19]), "+f"(d[20]), "+f"(d[21]), "+f"(d[22]), "+f"(d[23]), "+f"(d[24]), "+f"(d[25]), "+f"(d[26]), "+f"(d[27]), "+f"(d[28]), "+f"(d[29]), "+f"(d[30]), "+f"(d[31]), "+f"(d[32]), "+f"(d[33]), "+f"(d[34]), "+f"(d[35]), "+f"(d[36]), "+f"(d[37]), "+f"(d[38]), "+f"(d[39]), "+f"(d[40]), "+f"(d[41]), "+f"(d[42]), "+f"(d[43]), "+f"(d[44]), "+f"(d[45]), "+f"(d[46]), "+f"(d[47]), "+f"(d[48]), "+f"(d[49]), "+f"(d[50]), "+f"(d[51]), "+f"(d[52]), "+f"(d[53]), "+f"(d[54]), "+f"(d[55]), "+f"(d[56]), "+f"(d[57]), "+f"(d[58]), "+f"(d[59]), "+f"(d[60]), "+f"(d[61]), "+f"(d[62]), "+f"(d[63])
               : "r"(da), "r"(db), "n"(scale_d));
#undef R_
}
template <int scale_d> __device__ __forceinline__ void wgmma_n32(float* d, uint64_t descA, uint64_t descB) {
  asm volatile("{\n.reg .pred p;\nsetp.ne.b32 p, %18, 0;\n"
               "wgmma.mma_async.sync.aligned.m64n32k16.f32.bf16.bf16 {%0,%1,%2,%3,%4,%5,%6,%7,%8,%9,%10,%11,%12,%13,%14,%15}, %16, %17, p, 1, 1, 0, 1;\n}\n"
               : "+f"(d[0]), "+f"(d[1]), "+f"(d[2]), "+f"(d[3]), "+f"(d[4]), "+f"(d[5]), "+f"(d[6]), "+f"(d[7]), "+f"(d[8]), "+f"(d[9]), "+f"(d[10]), "+f"(d[11]), "+f"(d[12]), "+f"(d[13]), "+f"(d[14]), "+f"(d[15])
               : "l"(descA), "l"(descB), "n"(scale_d));
}
template <int scale_d, int tnsp_a> __device__ __forceinline__ void wgmma_n40(float* d, uint64_t descA, uint64_t descB) {
  asm volatile("{\n.reg .pred p;\nsetp.ne.b32 p, %22, 0;\n"
               "wgmma.mma_async.sync.aligned.m64n40k16.f32.bf16.bf16 {%0,%1,%2,%3,%4,%5,%6,%7,%8,%9,%10,%11,%12,%13,%14,%15,%16,%17,%18,%19}, %20, %21, p, 1, 1, %23, 1;\n}\n"
               : "+f"(d[0]), "+f"(d[1]), "+f"(d[2]), "+f"(d[3]), "+f"(d[4]), "+f"(d[5]), "+f"(d[6]), "+f"(d[7]), "+f"(d[8]), "+f"(d[9]), "+f"(d[10]), "+f"(d[11]), "+f"(d[12]), "+f"(d[13]), "+f"(d[14]), "+f"(d[15]), "+f"(d[16]), "+f"(d[17]), "+f"(d[18]), "+f"(d[19])
               : "l"(descA), "l"(descB), "n"(scale_d), "n"(tnsp_a));
}
template <int scale_d> __device__ __forceinline__ void wgmma_n40_rs(float* d, const uint32_t* a, uint64_t descB) {
  asm volatile("{\n.reg .pred p;\nsetp.ne.b32 p, %25, 0;\n"
               "wgmma.mma_async.sync.aligned.m64n40k16.f32.bf16.bf16 {%0,%1,%2,%3,%4,%5,%6,%7,%8,%9,%10,%11,%12,%13,%14,%15,%16,%17,%18,%19}, {%20,%21,%22,%23}, %24, p, 1, 1, 1;\n}\n"
               : "+f"(d[0]), "+f"(d[1]), "+f"(d[2]), "+f"(d[3]), "+f"(d[4]), "+f"(d[5]), "+f"(d[6]), "+f"(d[7]), "+f"(d[8]), "+f"(d[9]), "+f"(d[10]), "+f"(d[11]), "+f"(d[12]), "+f"(d[13]), "+f"(d[14]), "+f"(d[15]), "+f"(d[16]), "+f"(d[17]), "+f"(d[18]), "+f"(d[19])
               : "r"(a[0]), "r"(a[1]), "r"(a[2]), "r"(a[3]), "l"(descB), "n"(scale_d));
}
__device__ __forceinline__ void wgmma_copy(float* d, uint32_t da, uint64_t descB) {
  asm volatile("{\n.reg .pred p;\n.reg .b64 a;\nsetp.ne.b32 p, 0, 0;\nmov.b64 a, {%64, 0x40000040};\n"
               "wgmma.mma_async.sync.aligned.m64n16k16.f32.bf16.bf16 {%0,%1,%2,%3,%4,%5,%6,%7}, a, %65, p, 1, 1, 0, 0;\nadd.s64 a, a, 2;\n"
               "wgmma.mma_async.sync.aligned.m64n16k16.f32.bf16.bf16 {%8,%9,%10,%11,%12,%13,%14,%15}, a, %65, p, 1, 1, 0, 0;\nadd.s64 a, a, 2;\n"
               "wgmma.mma_async.sync.aligned.m64n16k16.f32.bf16.bf16 {%16,%17,%18,%19,%20,%21,%22,%23}, a, %65, p, 1, 1, 0, 0;\nadd.s64 a, a, 2;\n"
               "wgmma.mma_async.sync.aligned.m64n16k16.f32.bf16.bf16 {%24,%25,%26,%27,%28,%29,%30,%31}, a, %65, p, 1, 1, 0, 0;\nadd.s64 a, a, 1018;\n"
               "wgmma.mma_async.sync.aligned.m64n16k16.f32.bf16.bf16 {%32,%33,%34,%35,%36,%37,%38,%39}, a, %65, p, 1, 1, 0, 0;\nadd.s64 a, a, 2;\n"
               "wgmma.mma_async.sync.aligned.m64n16k16.f32.bf16.bf16 {%40,%41,%42,%43,%44,%45,%46,%47}, a, %65, p, 1, 1, 0, 0;\nadd.s64 a, a, 2;\n"
               "wgmma.mma_async.sync.aligned.m64n16k16.f32.bf16.bf16 {%48,%49,%50,%51,%52,%53,%54,%55}, a, %65, p, 1, 1, 0, 0;\nadd.s64 a, a, 2;\n"
               "wgmma.mma_async.sync.aligned.m64n16k16.f32.bf16.bf16 {%56,%57,%58,%59,%60,%61,%62,%63}, a, %65, p, 1, 1, 0, 0;\n"
               "}\n"
               : "+f"(d[0]), "+f"(d[1]), "+f"(d[2]), "+f"(d[3]), "+f"(d[4]), "+f"(d[5]), "+f"(d[6]), "+f"(d[7]), "+f"(d[8]), "+f"(d[9]), "+f"(d[10]), "+f"(d[11]), "+f"(d[12]), "+f"(d[13]), "+f"(d[14]), "+f"(d[15]), "+f"(d[16]), "+f"(d[17]), "+f"(d[18]), "+f"(d[19]), "+f"(d[20]), "+f"(d[21]), "+f"(d[22]), "+f"(d[23]), "+f"(d[24]), "+f"(d[25]), "+f"(d[26]), "+f"(d[27]), "+f"(d[28]), "+f"(d[29]), "+f"(d[30]), "+f"(d[31]), "+f"(d[32]), "+f"(d[33]), "+f"(d[34]), "+f"(d[35]), "+f"(d[36]), "+f"(d[37]), "+f"(d[38]), "+f"(d[39]), "+f"(d[40]), "+f"(d[41]), "+f"(d[42]), "+f"(d[43]), "+f"(d[44]), "+f"(d[45]), "+f"(d[46]), "+f"(d[47]), "+f"(d[48]), "+f"(d[49]), "+f"(d[50]), "+f"(d[51]), "+f"(d[52]), "+f"(d[53]), "+f"(d[54]), "+f"(d[55]), "+f"(d[56]), "+f"(d[57]), "+f"(d[58]), "+f"(d[59]), "+f"(d[60]), "+f"(d[61]), "+f"(d[62]), "+f"(d[63])
               : "r"(da), "l"(descB));
}
__device__ __forceinline__ uint64_t make_desc(uint32_t addr, uint32_t lbo_bytes, uint32_t sbo_bytes) {
  return (uint64_t)((addr & 0x3FFFF) >> 4) | ((uint64_t)(lbo_bytes >> 4) << 16) | ((uint64_t)(sbo_bytes >> 4) << 32) | (1ull << 62);
}

__device__ __forceinline__ void ldsm_x4(uint32_t addr, uint32_t& r0, uint32_t& r1, uint32_t& r2, uint32_t& r3) {
  asm volatile("ldmatrix.sync.aligned.m8n8.x4.shared.b16 {%0,%1,%2,%3}, [%4];" : "=r"(r0), "=r"(r1), "=r"(r2), "=r"(r3) : "r"(addr) : "memory");
}
__device__ __forceinline__ void ldsm_x4_t(uint32_t addr, uint32_t& r0, uint32_t& r1, uint32_t& r2, uint32_t& r3) {
  asm volatile("ldmatrix.sync.aligned.m8n8.x4.trans.shared.b16 {%0,%1,%2,%3}, [%4];" : "=r"(r0), "=r"(r1), "=r"(r2), "=r"(r3) : "r"(addr) : "memory");
}
__device__ __forceinline__ void stsm_x4(uint32_t addr, uint32_t r0, uint32_t r1, uint32_t r2, uint32_t r3) {
  asm volatile("stmatrix.sync.aligned.m8n8.x4.shared.b16 [%0], {%1,%2,%3,%4};" :: "r"(addr), "r"(r0), "r"(r1), "r"(r2), "r"(r3) : "memory");
}
__device__ __forceinline__ void stsm_x4_t(uint32_t addr, uint32_t r0, uint32_t r1, uint32_t r2, uint32_t r3) {
  asm volatile("stmatrix.sync.aligned.m8n8.x4.trans.shared.b16 [%0], {%1,%2,%3,%4};" :: "r"(addr), "r"(r0), "r"(r1), "r"(r2), "r"(r3) : "memory");
}
__device__ __forceinline__ void sts128(uint32_t addr, uint32_t a, uint32_t b, uint32_t c, uint32_t d) {
  asm volatile("st.shared.v4.u32 [%0], {%1,%2,%3,%4};" :: "r"(addr), "r"(a), "r"(b), "r"(c), "r"(d) : "memory");
}
__device__ __forceinline__ float lds32f(uint32_t addr) {
  float v;
  asm volatile("ld.shared.f32 %0, [%1];" : "=f"(v) : "r"(addr) : "memory");
  return v;
}
__device__ __forceinline__ void sts32f(uint32_t addr, float a) {
  asm volatile("st.shared.f32 [%0], %1;" :: "r"(addr), "f"(a) : "memory");
}
__device__ __forceinline__ void mma_bf16(float (&c)[4], uint32_t a0, uint32_t a1, uint32_t a2, uint32_t a3, uint32_t b0, uint32_t b1) {
  asm volatile("mma.sync.aligned.m16n8k16.row.col.f32.bf16.bf16.f32 {%0,%1,%2,%3}, {%4,%5,%6,%7}, {%8,%9}, {%0,%1,%2,%3};"
               : "+f"(c[0]), "+f"(c[1]), "+f"(c[2]), "+f"(c[3]) : "r"(a0), "r"(a1), "r"(a2), "r"(a3), "r"(b0), "r"(b1));
}
__device__ __forceinline__ void mma_bf16_z(float (&c)[4], uint32_t a0, uint32_t a1, uint32_t a2, uint32_t a3, uint32_t b0, uint32_t b1) {
  asm volatile("mma.sync.aligned.m16n8k16.row.col.f32.bf16.bf16.f32 {%0,%1,%2,%3}, {%4,%5,%6,%7}, {%8,%9}, {%10,%10,%10,%10};"
               : "=f"(c[0]), "=f"(c[1]), "=f"(c[2]), "=f"(c[3]) : "r"(a0), "r"(a1), "r"(a2), "r"(a3), "r"(b0), "r"(b1), "f"(0.f));
}
__device__ __forceinline__ uint32_t movm_t(uint32_t v) {
  uint32_t r;
  asm volatile("movmatrix.sync.aligned.m8n8.trans.b16 %0, %1;" : "=r"(r) : "r"(v));
  return r;
}
__device__ __forceinline__ uint32_t pack_bf16(float lo, float hi) {
  uint32_t r;
  asm("cvt.rn.bf16x2.f32 %0, %1, %2;" : "=r"(r) : "f"(hi), "f"(lo));
  return r;
}
__device__ __forceinline__ float bf_lo(uint32_t v) { return __uint_as_float(v << 16); }
__device__ __forceinline__ float bf_hi(uint32_t v) { return __uint_as_float(v & 0xFFFF0000u); }
__device__ __forceinline__ void split3(float x, uint32_t& h, uint32_t& m, uint32_t& l) {
  h = pack_bf16(x, 0.f); x -= bf_lo(h);
  m = pack_bf16(x, 0.f); x -= bf_lo(m);
  l = pack_bf16(x, 0.f);
}
__device__ __forceinline__ float ex2(float x) { float r; asm("ex2.approx.ftz.f32 %0, %1;" : "=f"(r) : "f"(x)); return r; }
__device__ __forceinline__ float rcp_fast(float x) { float r; asm("rcp.approx.ftz.f32 %0, %1;" : "=f"(r) : "f"(x)); return r; }
__device__ __forceinline__ void red_v4(float* p, float a, float b, float c, float d) {
  asm volatile("red.global.add.v4.f32 [%0], {%1, %2, %3, %4};" :: "l"(p), "f"(a), "f"(b), "f"(c), "f"(d) : "memory");
}
__device__ __forceinline__ uint4 ld_ll(const uint4* p) {
  uint4 v;
  asm volatile("{\n.reg .b64 a, b;\nld.relaxed.gpu.global.v2.b64 {a, b}, [%4];\nmov.b64 {%0, %1}, a;\nmov.b64 {%2, %3}, b;\n}\n"
               : "=r"(v.x), "=r"(v.y), "=r"(v.z), "=r"(v.w) : "l"(p) : "memory");
  return v;
}
__device__ __forceinline__ void st_b64(uint2* p, uint32_t a, uint32_t b) {
  asm volatile("{\n.reg .b64 v;\nmov.b64 v, {%1, %2};\nst.relaxed.gpu.global.b64 [%0], v;\n}\n" :: "l"(p), "r"(a), "r"(b) : "memory");
}
__device__ __forceinline__ void st_b128(uint4* p, uint32_t a, uint32_t b, uint32_t c, uint32_t d) {
  asm volatile("{\n.reg .b128 v;\nmov.b128 v, {%1, %2, %3, %4};\nst.relaxed.gpu.global.b128 [%0], v;\n}\n" :: "l"(p), "r"(a), "r"(b), "r"(c), "r"(d) : "memory");
}
__device__ __forceinline__ uint4 ld_b128(const uint4* p) {
  uint4 v;
  asm volatile("{\n.reg .b128 v;\nld.relaxed.gpu.global.b128 v, [%4];\nmov.b128 {%0, %1, %2, %3}, v;\n}\n" : "=r"(v.x), "=r"(v.y), "=r"(v.z), "=r"(v.w) : "l"(p) : "memory");
  return v;
}

constexpr float LOG2E = 1.4426950408889634f;

struct Params {
  const __nv_bfloat16* x0;
  const __nv_bfloat16* wA_qkv;
  const __nv_bfloat16* wA_o;
  const __nv_bfloat16* wB_qkv;
  const __nv_bfloat16* wB_phi;
  const __nv_bfloat16* wB_o;
  __nv_bfloat16* out;
};

#define ACC_DEF(d, n) _Pragma("unroll") for (int i_ = 0; i_ < (n); i_++) asm volatile("" : "=f"(d[i_]))
#define ACC_FENCE(d, n) _Pragma("unroll") for (int i_ = 0; i_ < (n); i_++) asm volatile("" : "+f"(d[i_]) :: "memory")
#define PIN(a, n) _Pragma("unroll") for (int i_ = 0; i_ < (n); i_++) asm volatile("" : "+f"((a)[i_]))
#define PINU(a, n) _Pragma("unroll") for (int i_ = 0; i_ < (n); i_++) asm volatile("" : "+r"((a)[i_]))

#define V_ADDR(p0, sw) uint32_t va_[2] = {(p0) + (srowoff >> 1) + (lhi ^ lsw2 ^ (sw)), (p0) + (srowoff >> 1) + ((32 + lhi) ^ lsw2 ^ (sw))}
#define STAGE_V(acc) { \
    _Pragma("unroll") for (int j_ = 0; j_ < 4; j_++) { \
      const float* a_ = (acc) + j_ * 8; \
      stsm_x4(va_[j_ & 1] + (j_ >> 1) * 8192, \
              pack_bf16(rs0 * a_[0], rs0 * a_[1]), pack_bf16(rs1 * a_[2], rs1 * a_[3]), pack_bf16(rs0 * a_[4], rs0 * a_[5]), pack_bf16(rs1 * a_[6], rs1 * a_[7])); } }
#define FRAG(dst, acc, TR, grp) { \
    _Pragma("unroll") for (int i_ = 15; i_ >= 0; i_--) { \
      const float r_ = (i_ & 8) ? rs1 : rs0; \
      const uint32_t w_ = pack_bf16(r_ * (acc)[4 * (i_ & 7) + (i_ >> 3) * 2], r_ * (acc)[4 * (i_ & 7) + (i_ >> 3) * 2 + 1]); \
      (dst)[8 + i_] = (TR) ? movm_t(w_) : w_; \
      if (i_ == 8 && warp >= 6 && mm < 15) { \
        _Pragma("unroll") for (int j_ = 0; j_ < 2; j_++) \
          st_b128(g_halo + (size_t)(mm * 8 + jj) * 512 + ((grp) * 4 + warp * 2 - 12 + j_) * 32 + lane, ((dst)[16 + j_ * 4] & ~1u) | H_BIT(l), (dst)[17 + j_ * 4], (dst)[18 + j_ * 4], (dst)[19 + j_ * 4]); } } \
    PINU((dst) + 8, 16); }
#define FRAG_PUT(src, slot) if (warp < 6) { _Pragma("unroll") for (int j_ = 0; j_ < 2; j_++) \
      sts128(sbase + (slot) * SLOT + 2048 + warp * 1024 + j_ * 512 + lane * 16, (src)[j_ * 4], (src)[j_ * 4 + 1], (src)[j_ * 4 + 2], (src)[j_ * 4 + 3]); }
#define FRAG_GET(dst, slot) { _Pragma("unroll") for (int j_ = 0; j_ < 2; j_++) \
      asm volatile("ld.shared.v4.u32 {%0, %1, %2, %3}, [%4];" : "=r"((dst)[j_ * 4]), "=r"((dst)[j_ * 4 + 1]), "=r"((dst)[j_ * 4 + 2]), "=r"((dst)[j_ * 4 + 3]) \
                   : "r"(sbase + (slot) * SLOT + warp * 1024 + j_ * 512 + lane * 16) : "memory"); }
#define RW(j) (((j) >> 1) * 4 + ((j) & 1))
template <int POS> __device__ __forceinline__ float exps16_(float* o, const float* p) {
  float s[4];
#pragma unroll
  for (int j = 0; j < 16; j++) { o[j] = ex2(POS ? p[RW(j)] : -p[RW(j)]); if (j < 4) s[j] = o[j]; else s[j & 3] += o[j]; }
  const float r = (s[0] + s[1]) + (s[2] + s[3]);
  return r + __shfl_xor_sync(0xffffffffu, r, 1);
}
template <int POS> __device__ __forceinline__ void exps16_fix(float* o, const float* p, float& sum) {
  if (__builtin_expect(__any_sync(0xffffffffu, !(sum > SUMLO && sum < SUMHI)), 0)) {
    float m = p[0], q[32];
#pragma unroll
    for (int j = 1; j < 16; j++) m = POS ? fmaxf(m, p[RW(j)]) : fminf(m, p[RW(j)]);
    const float x = __shfl_xor_sync(0xffffffffu, m, 1);
    m = POS ? fmaxf(m, x) : fminf(m, x);
#pragma unroll
    for (int j = 0; j < 16; j++) q[RW(j)] = p[RW(j)] - m;
    sum = exps16_<POS>(o, q);
  }
}
__device__ __forceinline__ void store16(const float* e, float sum, uint32_t dst, uint32_t dsw, int c0) {
  const float inv = rcp_fast(sum);
#pragma unroll
  for (int j = 0; j < 2; j++)
    sts128(dst + (((c0 + j) << 4) ^ dsw), pack_bf16(e[j * 8] * inv, e[j * 8 + 1] * inv), pack_bf16(e[j * 8 + 2] * inv, e[j * 8 + 3] * inv),
           pack_bf16(e[j * 8 + 4] * inv, e[j * 8 + 5] * inv), pack_bf16(e[j * 8 + 6] * inv, e[j * 8 + 7] * inv));
}
template <int POS> __device__ __forceinline__ void expp16(uint32_t* o, float* p) {
  {
#pragma unroll
    for (int r = 0; r < 4; r += 2) {
      float m = p[r];
#pragma unroll
      for (int j = 1; j < 8; j++) m = POS ? fmaxf(m, p[r + RW(j)]) : fminf(m, p[r + RW(j)]);
#pragma unroll
      for (int s = 1; s <= 2; s <<= 1) { const float x = __shfl_xor_sync(0xffffffffu, m, s); m = POS ? fmaxf(m, x) : fminf(m, x); }
#pragma unroll
      for (int j = 0; j < 8; j++) p[r + RW(j)] -= m;
    }
  }
#pragma unroll
  for (int j = 0; j < 8; j++) o[j] = pack_bf16(ex2(POS ? p[2 * j] : -p[2 * j]), ex2(POS ? p[2 * j + 1] : -p[2 * j + 1]));
}
__device__ __forceinline__ void scale32(float* o, const float* p, float c0, float c1) {
#pragma unroll
  for (int i = 0; i < 32; i++) asm volatile("mul.f32 %0, %1, %2;" : "=f"(o[i]) : "f"(p[i]), "f"((i & 2) ? c1 : c0));
}
__device__ __forceinline__ bool any_big(const float* p) {
  float m[4];
#pragma unroll
  for (int i = 0; i < 32; i++) m[i >> 3] = (i & 7) ? fmaf(p[i], p[i], m[i >> 3]) : p[i] * p[i];
  return __any_sync(0xffffffffu, !(fmaxf(fmaxf(m[0], m[1]), fmaxf(m[2], m[3])) < BIGLIM));
}
__device__ __forceinline__ void phiq_a(float* p, bool big) {
  if (__builtin_expect(!big, 1)) {
#pragma unroll
    for (int j = 0; j < 16; j++) p[j] = ex2(p[j]);
  }
}
template <int NEXT> __device__ __forceinline__ void phiq_b(uint32_t* o, float* p, bool big) {
  if (__builtin_expect(big, 0)) {
    expp16<0>(o, p); expp16<1>(o + 8, p);
  } else {
    if (NEXT) phiq_a(p + 16, false);
#pragma unroll
    for (int j = 0; j < 4; j++) {
      const float a = p[4 * j], b = p[4 * j + 1], c = p[4 * j + 2], d = p[4 * j + 3];
      const float ab = a * b, cd = c * d, r = rcp_fast(ab * cd), x = r * cd, y = r * ab;
      o[2 * j] = pack_bf16(x * b, x * a); o[2 * j + 1] = pack_bf16(y * d, y * c);
      o[8 + 2 * j] = pack_bf16(a, b); o[9 + 2 * j] = pack_bf16(c, d);
    }
  }
}
#define SCHED_FENCE() asm volatile("pmevent 0;" ::: "memory")

__global__ void __cluster_dims__(2, 1, 1) __launch_bounds__(384, 1)
mega_kernel(const __grid_constant__ CUtensorMap tm_x0, const __grid_constant__ CUtensorMap tm_xo, const __grid_constant__ CUtensorMap tm_os,
            const __grid_constant__ CUtensorMap tm_o, const __grid_constant__ CUtensorMap tm_wf,
            const __grid_constant__ CUtensorMap tm_wqA, const __grid_constant__ CUtensorMap tm_wqB,
            const __grid_constant__ CUtensorMap tm_woA, const __grid_constant__ CUtensorMap tm_woB,
            const __grid_constant__ CUtensorMap tm_phi, const Params prm) {
  extern __shared__ __align__(1024) uint8_t smem_raw[];
  const uint32_t sbase = smem_u32(smem_raw);
  const uint32_t bar_full = sbase + OFF_BAR;
  const uint32_t bar_done = bar_full + 384;
  const uint32_t bar_stat = bar_full + 768, bar_stat2 = bar_full + 776, bar_epi = bar_full + 784, bar_phi = bar_full + 936  , bar_halo = bar_full + 904  ;
  const uint32_t bar_xr = bar_full + 800, bar_lx = bar_full + 808, bar_stg = bar_full + 832;
  const uint32_t bar_chk = bar_full + 848;

  const int warp = __shfl_sync(0xffffffffu, threadIdx.x >> 5, 0), lane = threadIdx.x & 31;
  const uint32_t bar_kx = sbase + OFF_ID + 384 + warp * 8;
  uint32_t rank;
  asm volatile("mov.u32 %0, %%cluster_ctarank;" : "=r"(rank));
  const int aux = (int)blockIdx.x - NMAIN, tp = (int)(blockIdx.x >> 1) - 4;
  const int gp = tp < 0 ? 0 : (tp < 32 ? tp & 7 : 1 + (tp - 32) % 7), me = tp < 0 ? tp + 8 : (tp < 32 ? tp >> 3 : 4 + (tp - 32) / 7);
  const int jj = me, cc = gp;
  const int cta = aux >= 0 ? -1 : (cc * 8 + jj) * 2 + (int)rank;
  const int mm = cc * 2 + (int)rank;

#define LOAD_EPOCH() const unsigned epoch = ld_relaxed(&g_flags.epoch.v), ep1 = epoch + 1; (void)epoch
  int budget = 1 << 22;

  if (cta >= 0) {
    if (warp >= 8 && warp < 8 + EARLY && elect_one()) {
      const int u = warp - 8;
      const uint32_t fb = bar_full + u * 8;
      mbar_init(fb, 1);
      asm volatile("fence.mbarrier_init.release.cluster;" ::: "memory");
      fence_proxy_async_smem();
      mbar_expect_tx(fb, QST + SLOT);
      if (u) __nanosleep(STAG2);
      tma_load_t(sbase + OFF_S + u * SLOT, &tm_x0, fb, jj * 128 + u * 64, mm * 128);
#pragma unroll
      for (int i = 0; i < 6; i++) tma_load_2d(sbase + u * QST + i * 4096, &tm_wqA, fb, jj * 128 + (i >> 1) * 1024, jj * 128 + u * 64 + (i & 1) * 32);
      if (u == 0) PROFT(472);
    }
    __syncwarp();
    {
      const int tx = threadIdx.x;
      const __nv_bfloat16* pf = (tx < 128) ? prm.x0 + (size_t)(mm * 128 + tx) * D_MODEL + jj * 128
                                           : prm.wA_qkv + (size_t)(jj * 128 + (tx & 63)) * 3072 + ((tx - 128) >> 6) * 1024 + jj * 128 + rank * 64;
      if (tx < 320) asm volatile("prefetch.global.L2 [%0];" :: "l"(pf));
      else if (tx == 320) prefetch_tmap(&tm_x0);
      else if (tx == 352) prefetch_tmap(&tm_wqA);
      else if (tx == 383) asm volatile("prefetch.global.L2 [%0];" :: "l"(&g_flags.epoch.v));
    }
    if (elect_one()) {
#pragma unroll
      for (int i = 0; i < 4; i++) {
        const int u = warp * 4 + i;
        if (u >= EARLY) mbar_init(bar_full + u * 8, ((u >= 4 && u < 11) || (u > 32 && u != 40)) ? 2 : 1); mbar_init(bar_done + u * 8, 16);
      }
      mbar_init(bar_stat + warp * 16, 0x111111181182ull >> (4 * warp) & 15);
      mbar_init(bar_stat + warp * 16 + 8, 0x111111121811ull >> (4 * warp) & 15);
      mbar_init(bar_chk + 112 + (warp & 7) * 8, 1);
      mbar_init(bar_kx, 1);
      asm volatile("fence.mbarrier_init.release.cluster;" ::: "memory");
    }
    __syncwarp();
    __syncthreads();
    asm volatile("barrier.cluster.arrive.relaxed.aligned;" ::: "memory");
  }

  if (cta < 0) {
    LOAD_EPOCH();
    const uint32_t buf = sbase + warp * SLOT, bar = sbase + OFF_BAR + warp * 16;
    const uint32_t lsw = (lane & 7) << 4, lhi = (lane >> 4) << 4, lrow = (lane & 15) * 128;
    const bool el = elect_one();
    if (el) {
      mbar_init(bar, 1); mbar_init(bar + 8, 1);
      asm volatile("fence.mbarrier_init.release.cluster;" ::: "memory");
    }
#pragma unroll 1
    for (int rd = 0; rd < (NLAYERS > 1 ? 5 : 2); rd++) {
      if (rd >= 2 && warp >= 8) break;
      const int tk = rd < 2 ? aux * 12 + warp : aux * 8 + warp;
      const int half = tk & 1;
      const int blk = rd < 2 ? (tk >> 1) * 2 + rd : (4 - rd) * 16 + (tk >> 1);
      const CUtensorMap* tm = rd < 2 ? &tm_wqA : (rd == 2 ? &tm_wqB : &tm_wf);
      const int j0 = (blk & 15) >> 1;
#define AUX_LOAD(n) { const uint32_t d_ = buf + ((n) & 1) * 8192, b_ = bar + ((n) & 1) * 8; const int r_ = kslice(j0, 2 * (n) + half) * 64; \
        mbar_expect_tx(b_, 8192); tma_load_2d(d_, tm, b_, blk * 64, r_); tma_load_2d(d_ + 4096, tm, b_, blk * 64, r_ + 32); }
      if (el) {
        if (rd == 3) { wait_flag(&g_flags.wfready[j0].v, ep1 * 16); fence_proxy_async_global(); }
        AUX_LOAD(0); AUX_LOAD(1);
      }
      __syncwarp();
      float cs[8][4];
#pragma unroll
      for (int i = 0; i < 8; i++) cs[i][0] = cs[i][1] = cs[i][2] = cs[i][3] = 0.f;
#pragma unroll 1
      for (int n = 0; n < 8; n++) {
        const uint32_t tb = buf + (n & 1) * 8192 + lrow;
        mbar_wait(bar + (n & 1) * 8, (n >> 1) & 1);
#pragma unroll
        for (int i = 0; i < 16; i++) {
          uint32_t b0, b1, b2, b3;
          ldsm_x4_t(tb + (i >> 2) * 2048 + (((i & 3) * 32 + lhi) ^ lsw), b0, b1, b2, b3);
          mma_bf16(cs[2 * (i & 3)], 0x3F803F80u, 0x3F803F80u, 0x3F803F80u, 0x3F803F80u, b0, b1);
          mma_bf16(cs[2 * (i & 3) + 1], 0x3F803F80u, 0x3F803F80u, 0x3F803F80u, 0x3F803F80u, b2, b3);
        }
        __syncwarp();
        if (el && n < 6) AUX_LOAD(n + 2);
        __syncwarp();
      }
      if (lane < 4) {
#pragma unroll
        for (int i = 0; i < 8; i++) st_b64(&g_colsum[rd >= 2][blk * 32 + i * 4 + lane][half], __float_as_uint(cs[i][0]), (__float_as_uint(cs[i][1]) & ~3u) | (ep1 & 3));
      }
      __syncwarp();
    }
  } else if (warp >= 8) {
    asm volatile("setmaxnreg.dec.sync.aligned.u32 40;");
    if (warp == 8) {
      const bool el = elect_one();
      cluster_wait();
      if (el) {
#pragma unroll 1
        for (int l = 0; l < NLAYERS; l++) {
          const uint32_t par = l & 1;
          const CUtensorMap* tqk = par ? &tm_wf : &tm_wqA;
          const CUtensorMap* tv = par ? &tm_wqB : &tm_wqA;
          const CUtensorMap* two = par ? &tm_woB : &tm_woA;
          if (l == 1) { LOAD_EPOCH(); wait_flag(&g_flags.wfready[jj].v, ep1 * 16); fence_proxy_async_global(); }
#pragma unroll 1
          for (int u = l ? 0 : EARLY; u < 32; u++) {
            if (u >= 4) mbar_wait_sl(bar_done + (u - 4) * 8, par);
            else if (l) mbar_wait_sl(bar_done + (43 + u + (u >> 1)) * 8, par ^ 1);
            else mbar_wait_sl(bar_full, 0);
            const uint32_t fb = bar_full + u * 8;
            const bool res = u < 11 || (u >= 18 && u < 22);
            mbar_expect_tx(fb, res ? QST : QST + SLOT);
            const int row = kslice(jj, u < 4 ? u & 1 : (u < 18 ? u - 2 : (u < 22 ? u - 6 : u - 20))) * 64 + (int)rank * 32;
            const int ps = u < 4 ? u >> 1 : (u >= 18), col = jj * 128 + ps * 64;
            const int c0 = par ? jj * 128 + (ps ? 0 : 1024) : col;
            const uint32_t dst = sbase + (u & 3) * QST + rank * 4096;
            tma_load_2d_mc(dst, tqk, fb, c0, row);
            tma_load_2d_mc(dst + 8192, tqk, fb, c0 + (par ? 64 : 1024), row);
            tma_load_2d_mc(dst + 16384, tv, fb, col + 2048, row);
            if (l == PRL && u >= PRU && u < PRU + 4) PROFT(473 + u - PRU);
          }
#pragma unroll 1
          for (int s = 0; s < 16; s++) {
            if (s < 5) { if (s != 2 && s != 4) mbar_wait_sl(bar_done + (28 + s) * 8, par); }
            else if (s != 14) mbar_wait_sl(bar_done + (27 + s - (s == 15)) * 8, par);
            const uint32_t fb = bar_full + (32 + s) * 8;
            mbar_expect_tx(fb, SLOT);
            tma_load_2d_mc(sbase + rank * 8192 + (uint32_t)((WO_BSLOT >> (4 * s)) & 15) * SLOT, two, fb, jj * 128 + (int)rank * 64, wslice(jj, s) * 64);
            const int ts = s + par;
            if (s >= 5 && ts < 8) {
              mbar_expect_tx(bar_chk - 8 + ts * 8, SLOT);
              tma_load_t(sbase + (uint32_t)((WO_ASLOT(par) >> (4 * ts)) & 15) * SLOT, &tm_o, bar_chk - 8 + ts * 8, wslice(jj, ts) * 64, mm * 128);
            }
          }
        }
      }
      __syncwarp();
    } else if (warp == 9) {
      const bool el = elect_one();
      LOAD_EPOCH();
#pragma unroll 1
      for (int lp = 0; lp < 4 * NLAYERS; lp++) {
        const int l = lp >> 2, ph = lp & 3;
        if (ph == 3) continue;
        const uint32_t par = l & 1;
        const unsigned* pp = reinterpret_cast<const unsigned*>(g_obuf + (ph >> 1) * 64 + (size_t)(mm * 128 + (ph ? 0 : S_LEN) + ((lane & 7) | PROWS) * 16 + (jj & 1) * 8) * D_MODEL +
                                                               (jj >> 1) * 16 + srcb(jj, lane >> 3) * 128);
        const CUtensorMap* tm = lp ? &tm_o : &tm_x0;
        const int row = mm * 128 + ((ph || !l) ? 0 : S_LEN);
        const uint32_t bit = ph ? O_BIT(l) : X_BIT(l - 1);
        const uint32_t slots = ph ? (uint32_t)(WO_ASLOT(par) >> (ph * 32 - 28)) : 0x8769876u;
        const unsigned long long fr = ph == 0 ? XPACE : ph == 1 ? (par ? FRB : 0x35351F1Eull) : (par ? 0x27262524232232ull : 0x27262524233232ull);
        uint32_t no = (lp == 0 || (lp & 7) == 1) ? 0 : (ph == 1 ? NOB : (ph ? NO1 : NOX)), v0 = 0, v1 = 0;
        mbar_wait_sl(ph ? bar_done + ((uint32_t)fr & 63) * 8 : (l ? bar_done + 47 * 8 : bar_full), ph ? par : (l ? par ^ 1 : 0));
        if (el && ph) PROFT(324 + l * 16 + ph);
        __syncwarp();
        if (no && (ph == 1 ? SPD1 : (ph ? SPD2 : SPD0))) __nanosleep(ph == 1 ? SPD1 : (ph ? SPD2 : SPD0));
        if (no) { v0 = ld_relaxed(pp); __nanosleep(POLLGAP); v1 = ld_relaxed(pp); }
#pragma unroll 1
        for (int i = 0; i < (ph == 1 ? 4 + par : 7); i++, no >>= 8) {
#pragma unroll 1
          for (int it = 0; (no & 0xFF) && it < (1 << 18); it++) {
            no &= __ballot_sync(0xffffffffu, (v0 ^ bit) & 1) >> (8 * i);
            if (no) v0 = ld_relaxed(pp);
            if (!(no & 0xFF)) break;
            no &= __ballot_sync(0xffffffffu, (v1 ^ bit) & 1) >> (8 * i);
            if (no) v1 = ld_relaxed(pp);
          }
          if (ph || i >= XP0) mbar_wait_sl(bar_done + ((uint32_t)(fr >> (8 * i)) & 63) * 8, par);
          if (el) {
            if (i == 0) PROFT(320 + l * 16 + ph);
            const uint32_t cb = (lp ? bar_chk + (ph >> 1) * 112 : bar_full + 32) + i * 8;
            mbar_expect_tx(cb, SLOT);
            tma_load_t(sbase + ((slots >> (4 * i)) & 15) * SLOT, tm, cb, srcb(jj, i) * 128 + (ph >> 1) * 64, row);
          }
          __syncwarp();
        }
        if (ph == 0 && el) {
          if (l) { wait_flag(&g_flags.xready[l][mm].v, ep1 * 8); fence_proxy_async_global(); }
#pragma unroll 1
          for (int u = 11; u < 34; u++) {
            if (u == 18) u = 22;
            mbar_wait_sl(bar_done + (u - 4) * 8, par);
            if (u == 32) mbar_expect_tx(bar_xr, 2 * SLOT);
            tma_load_t(sbase + OFF_RA + (u & 3) * SLOT, tm, u < 32 ? bar_full + u * 8 : bar_xr, kslice(jj, u < 18 ? u - 2 : (u < 32 ? u - 20 : u - 32)) * 64, row);
          }
        }
        __syncwarp();
      }
      if (el && atomicAdd(&g_flags.done.v, 1) == ep1 * NMAIN - 1) asm volatile("st.relaxed.gpu.global.u32 [%0], %1;" :: "l"(&g_flags.epoch.v), "r"(ep1) : "memory");
      __syncwarp();
      cluster_wait();
    } else {
      const int hw = warp - 10;
      LOAD_EPOCH();
      const bool el = elect_one();
      cluster_wait();
      if (hw == 0) {
        mbar_wait_sl(bar_full + 8, 0);
        if (lane < 7) prefetch_tmap(lane == 0 ? &tm_os : lane == 1 ? &tm_o : lane == 2 ? &tm_wf : lane == 3 ? &tm_wqB : lane == 4 ? &tm_woA : lane == 5 ? &tm_woB : &tm_phi);
#pragma unroll 1
        for (int i = 0; i < (NLAYERS > 1 ? 9 : 0); i++) {
          if (i == 0 || i == 5) mbar_wait_sl(bar_done + (i ? FD1 : FD0) * 8, 0);
          if (el) {
            if (i == 0) { mbar_expect_tx(bar_phi, 2 * SLOT + 8192); tma_load_2d(sbase + OFF_PHI, &tm_phi, bar_phi, 0, jj * 128); }
            else tma_load_2d(sbase + (i > 4 ? 10 : 12) * SLOT - 4096 + i * 4096, &tm_wqB, bar_phi, (i > 4 ? 896 : 0) + jj * 128 + ((i - 1) >> 1) * 64, mm * 64 + (~i & 1) * 32);
          }
          __syncwarp();
          __nanosleep(PFGAP);
        }
      } else {
        if (lane < 24) {
          const uint32_t one = (lane & 8) ? 0u : 0x3F80u << ((lane & 1) * 16), w = (lane >> 1) & 3;
          sts128(sbase + OFF_ID + lane * 16, w == 0 ? one : 0u, w == 1 ? one : 0u, w == 2 ? one : 0u, w == 3 ? one : 0u);
        }
#pragma unroll 1
        for (int b = 0; b < 2; b++) {
          float4* z = reinterpret_cast<float4*>(g_kv[b] + (jj * 4) * KVH + mm * (4 * KVH / 16)) + lane;
#pragma unroll
          for (int i = 0; i < 6; i++) z[i * 32] = make_float4(0.f, 0.f, 0.f, 0.f);
        }
#pragma unroll 1
        for (int i = 0; i < 16; i++) {
          const int b = i >> 2;
          const uint32_t v = (b == 0 ? O_BIT(0) : b == 1 ? X_BIT(0) : H_BIT(0)) + 1;
          uint4* p = b < 2 ? reinterpret_cast<uint4*>(g_obuf + (size_t)(b * S_LEN + mm * 128 + (i & 3) * 32 + (lane >> 3) * 8) * D_MODEL + jj * 128 + (b ? 0 : 64)) + (lane & 7)
                           : g_halo + (size_t)(mm * 8 + jj) * 512 + i * 32 + lane;
          *p = make_uint4(v, v, v, v);
        }
        fence_proxy_async_global();
      }
      __syncwarp();
      uint32_t chkp = 0;
#pragma unroll 1
      for (int lp = hw; lp < 8 * NLAYERS; lp++) {
        const int l = lp >> 3, tk = lp & 7, ph = tk ? 2 - hw : 0;
        const uint32_t par = l & 1;
        int lane; asm volatile("mov.u32 %0, %%laneid;" : "=r"(lane));
        if (tk == 5 || (hw && tk == 0)) {
          const uint32_t bit = ph ? O_BIT(l) : X_BIT(l - 1);
          uint32_t slots = ph ? (uint32_t)(WO_ASLOT(par) >> (ph * 32 - 28)) : 0x8769876u;
          const uint32_t a0 = sbase + (lane & 7) * 126 + lane * 4 + (lane & 1) * 14;
#pragma unroll 1
          for (int c = 0; c < 7; c++, slots >>= 4) {
            const uint32_t cb = bar_chk + 112 - hw * 112 + c * 8;
#pragma unroll 1
            for (int it = 0; it < (1 << 12); it++) {
              mbar_wait_sl(cb, (chkp >> c) & 1);
              chkp ^= 1u << c;
              if (el && c == 0) PROFT(ph == 1 ? 480 + l * 2 : 488 + l * 2 + (ph >> 1));
              uint32_t bad;
              asm volatile("{\n.reg .b32 w<16>;\n"
                           "ld.shared.u32 w0, [%1 + 0];\n"
                           "ld.shared.u32 w1, [%1 + 1024];\n"
                           "ld.shared.u32 w2, [%1 + 2048];\n"
                           "ld.shared.u32 w3, [%1 + 3072];\n"
                           "ld.shared.u32 w4, [%1 + 4096];\n"
                           "ld.shared.u32 w5, [%1 + 5120];\n"
                           "ld.shared.u32 w6, [%1 + 6144];\n"
                           "ld.shared.u32 w7, [%1 + 7168];\n"
                           "ld.shared.u32 w8, [%1 + 8192];\n"
                           "ld.shared.u32 w9, [%1 + 9216];\n"
                           "ld.shared.u32 w10, [%1 + 10240];\n"
                           "ld.shared.u32 w11, [%1 + 11264];\n"
                           "ld.shared.u32 w12, [%1 + 12288];\n"
                           "ld.shared.u32 w13, [%1 + 13312];\n"
                           "ld.shared.u32 w14, [%1 + 14336];\n"
                           "ld.shared.u32 w15, [%1 + 15360];\n"
                           "lop3.b32 w0, w0, w1, %2, 0x7E;\n"
                           "lop3.b32 w2, w2, w3, %2, 0x7E;\n"
                           "lop3.b32 w4, w4, w5, %2, 0x7E;\n"
                           "lop3.b32 w6, w6, w7, %2, 0x7E;\n"
                           "lop3.b32 w8, w8, w9, %2, 0x7E;\n"
                           "lop3.b32 w10, w10, w11, %2, 0x7E;\n"
                           "lop3.b32 w12, w12, w13, %2, 0x7E;\n"
                           "lop3.b32 w14, w14, w15, %2, 0x7E;\n"
                           "lop3.b32 w0, w0, w2, w4, 0xFE;\nlop3.b32 w6, w6, w8, w10, 0xFE;\nlop3.b32 w0, w0, w12, w14, 0xFE;\nlop3.b32 %0, w0, w6, 1, 0xA8;\n}\n"
                           : "=r"(bad) : "r"(a0 + (slots & 15) * SLOT), "r"(bit) : "memory");
              if (__all_sync(0xffffffffu, bad == 0)) break;
              if (el) {
                fence_proxy_async_smem();
                mbar_expect_tx(cb, SLOT);
                tma_load_t(sbase + (slots & 15) * SLOT, &tm_o, cb, srcb(jj, c) * 128 + (ph >> 1) * 64, mm * 128 + (ph ? 0 : S_LEN));
                RETRY_COUNT();
              }
              __syncwarp();
            }
            if (el) { mbar_arrive_local(bar_full + (c + (ph ? 25 + ph * 8 : 4)) * 8); if (lp == PRL * 8 && c == 0) PROFT(477); }
            __syncwarp();
          }
        } else if (hw && (tk & 5) == 1) {
          {
            const int hp = tk >> 1;
            const uint4* src = reinterpret_cast<const uint4*>(g_colsum[par][jj * 64 + hp * 32 + lane]);
            uint32_t bad;
            int it = 0;
            float c[6];
            do {
              bad = 0;
#pragma unroll
              for (int p = 0; p < 3; p++) {
                const uint4 v = ld_ll(src + ((par && p < 2) ? (hp ? -32 : 512) + p * 32 : p * 512));
                bad |= (v.y ^ ep1) | (v.w ^ ep1);
                c[2 * p] = __uint_as_float(v.x) + __uint_as_float(v.z); c[2 * p + 1] = __uint_as_float(v.y) + __uint_as_float(v.w);
              }
              bad &= 3;
              if (bad) __nanosleep(300);
            } while (bad && ++it < (1 << 16));
#pragma unroll
            for (int p = 0; p < 6; p++) {
              uint32_t h, m, lo;
              split3(c[p], h, m, lo);
              sts128(sbase + OFF_LNB + hp * 4096 + (p >> 1) * 1024 + lane * 32 + (p & 1) * 16, h | (m << 16), h | (lo << 16), h | (m << 16), lo | (m << 16));
            }
            fence_proxy_async_smem();
            __syncwarp();
            if (el) { mbar_arrive_local(hp ? bar_stat2 : bar_stat); if (hp == 0) PROFT(324 + l * 16); }
            __syncwarp();
          }
        } else if (tk == 0) {
          mbar_wait_sl(bar_done + 24, par);
          const uint4* sp = reinterpret_cast<const uint4*>(g_stats + (size_t)(mm * 128) * 8) + lane;
#pragma unroll 1
          for (int hf = 0; hf < 4; hf++) {
            uint4 v[4];
            uint32_t bad;
            int it = 0;
            do {
              bad = 0;
#pragma unroll
              for (int i = 0; i < 4; i++) { v[i] = ld_ll(sp + (hf * 4 + i) * 32); bad |= (v[i].y ^ STAT_TAG(l)) | (v[i].w ^ STAT_TAG(l)); }
              bad &= 3;
              if (bad) __nanosleep(200);
            } while (bad && ++it < (1 << 16));
            __syncwarp();
            float mean = 0.f, m2 = 0.f;
#pragma unroll
            for (int i = 0; i < 4; i++) {
              float a = __uint_as_float(v[i].x) + __uint_as_float(v[i].z);
              a += __shfl_xor_sync(0xffffffffu, a, 1); a += __shfl_xor_sync(0xffffffffu, a, 2);
              a *= 0.125f;
              const float e0 = __uint_as_float(v[i].x) - a, e1 = __uint_as_float(v[i].z) - a;
              float q = fmaf(fmaf(e0, e0, e1 * e1), 128.f, __uint_as_float(v[i].y) + __uint_as_float(v[i].w));
              q += __shfl_xor_sync(0xffffffffu, q, 1); q += __shfl_xor_sync(0xffffffffu, q, 2);
              if ((lane & 3) == i) { mean = a; m2 = q; }
            }
            const uint32_t row = hf * 32 + (lane & 3) * 8 + (lane >> 2);
            uint32_t h, m, lo;
            split3(-0.5f * mean, h, m, lo);
            sts128(sbase + OFF_LNA + row * 16, h | (h << 16), m | (h << 16), lo | (m << 16), m | (lo << 16));
            sts32f(sbase + OFF_ST + row * 4, rsqrtf(m2 * (1.f / 1024.f) + 1e-5f));
          }
          fence_proxy_async_smem();
          __syncwarp();
          if (el) { mbar_arrive_local(bar_stat); PROFT(323 + l * 16); }
          __syncwarp();
#pragma unroll 1
          for (int i = 0; i < 8 - 4 * l; i++) {
            asm volatile("prefetch.global.L2 [%0];" :: "l"(i < 4 ? (l ? prm.wB_o : prm.wA_o) + (size_t)cta * 8192 + i * 2048 + lane * 64
                                                                 : prm.wB_qkv + (size_t)(cta * 8 + (i - 4) * 2 + (lane >> 4)) * 3072 + 2048 + (lane & 15) * 64));
            __nanosleep(PFGAP);
          }
        } else if (lp == 3) {
#pragma unroll 1
          for (int c = 0; c < (NLAYERS > 1 ? 8 : 0); c++) {
            if (!(c & 3)) asm volatile("bar.sync %0, 288;" :: "r"(BAR_WF + (c >> 2)) : "memory");
            if (el) {
              tma_store_2d(&tm_wf, sbase + 11 * SLOT + c * 4096, (c < 4 ? 1024 : -128) + jj * 128 + (c >> 1) * 64, mm * 64 + (c & 1) * 32);
              if ((c & 3) == 3) {
                asm volatile("cp.async.bulk.commit_group;\ncp.async.bulk.wait_group.read 0;" ::: "memory");
                mbar_arrive_local(bar_phi + (c >> 2) * 8);
              } else __nanosleep(WFGAP);
            }
            __syncwarp();
          }
          if (el) { bulk_commit_wait(); signal_release(&g_flags.wfready[jj].v); PROFT(335); }
          __syncwarp();
        } else if (tk == 2 || tk == 4) {
          if (par) continue;
          const int i = tk >> 2;
          mbar_wait_sl(bar_done + (i ? HW1 : (hw ? 19 : HW0)) * 8, 0);
          const uint4* src = g_halo + (size_t)(mm * 8 + jj - 8) * 512 + i * 256 + hw * 128 + lane;
          uint4 v[4];
          int it = 0;
          bool ok;
          do {
#pragma unroll
            for (int j = 0; j < 4; j++) v[j] = mm ? ld_b128(src + j * 32) : make_uint4(H_BIT(l), 0, 0, 0);
            ok = __all_sync(0xffffffffu, (((v[0].x ^ H_BIT(l)) | (v[1].x ^ H_BIT(l)) | (v[2].x ^ H_BIT(l)) | (v[3].x ^ H_BIT(l))) & 1) == 0);
          } while (!ok && ++it < (1 << 16));
          if (lp + hw == 3 && NLAYERS > 1) mbar_wait_sl(bar_phi, 1);
#pragma unroll
          for (int j = 0; j < 4; j++) sts128(sbase + OFF_S + hw * SLOT + j * 512 + lane * 16, v[j].x, v[j].y, v[j].z, v[j].w);
          __syncwarp();
          if (el) { mbar_arrive_local(bar_halo + hw * 8); PROFT(331 + l * 16 + i * 2 + hw); }
          __syncwarp();
        } else if (tk == 6 && hw == 0 && l < NLAYERS - 1) {
          bar_sync<BAR_X1, 288>();
          if (el) {
            PROFT(328 + l * 16);
            mbar_wait_sl(bar_full + XD * 8, par ^ 1);
            tma_store_t(&tm_o, sbase + 11 * SLOT, jj * 128 + 64, mm * 128 + S_LEN);
            bulk_commit_wait();
            signal_release(&g_flags.xready[l + 1][mm].v);
            PROFT(330 + l * 16);
          }
          __syncwarp();
        }
      }
    }
    cluster_sync();
  } else {
    asm volatile("setmaxnreg.inc.sync.aligned.u32 232;");
    const int wg = warp >> 2;
    const int r0 = warp * 16;
    const uint32_t pK = sbase + OFF_S, pV = sbase + OFF_S + SLOT;
#define PMASKS(on, bit) const uint32_t pm0 = ((on) && t == (g >> 1)), pbit = (bit)
#define PBIT(w) (((w) & ~pm0) | (pbit & pm0))
#define LANE_CONSTS() \
    int lane; asm volatile("mov.u32 %0, %%laneid;" : "=r"(lane)); \
    const int g = lane >> 2, t = lane & 3; \
    const uint32_t srowoff = (r0 + (lane & 15)) * 128, lsw = (lane & 7) << 4, lhi = (lane >> 4) << 4, lsw2 = (lane & 6) << 3; \
    (void)g; (void)t; (void)srowoff; (void)lsw; (void)lhi; (void)lsw2;
    uint32_t stgp = 0, peer;
    asm volatile("mapa.shared::cluster.u32 %0, %1, %2;" : "=r"(peer) : "r"(sbase), "r"(rank ^ 1));
    peer -= sbase;
    const uint32_t dA0 = (((sbase & 0x3FFFF) + wg * 8192) >> 4) | 0x10000u, dB0 = ((sbase & 0x3FFFF) >> 4) | 0x2000000u;
    cluster_wait();
#define DESC(lo, hi) ((uint64_t)(uint32_t)(lo) | ((uint64_t)(hi) << 32))
#define STG_ARRIVE() { __syncwarp(); if (elect_one()) mbar_arrive_local(bar_stg); }
#define STG_WAIT() { mbar_wait(bar_stg, stgp); stgp ^= 1; }
#define PROFS() do {} while (0)
#define REL(addr) { if (elect_one()) { mbar_arrive_local(addr); asm volatile("mbarrier.arrive.shared::cluster.b64 _, [%0];" :: "r"((addr) + peer) : "memory"); } }
#define QSTEP(ACC, DA, SC) { \
      const uint32_t da = (DA), db = dB0 + (ub & 0x18) * (QST >> 7); \
      mbar_wait(ub, par); \
      wgmma_fence(); \
      wgmma4_n192<SC>(ACC, da, db); \
      wgmma_commit(); PROFS(); }
#define QREL() { wgmma_wait<1>(); REL(ub + 376); ub += 8; }
#define RA_CUR (dA0 + (OFF_RA >> 4) + (ub & 0x18) * (SLOT >> 7))
#define PUMP1() { QSTEP(S1, RA_CUR, 1); QREL(); }
#define PUMPN() { wgmma_fence(); wgmma4_n192<1>(S1, RA_CUR, dB0 + (ub & 0x18) * (QST >> 7)); wgmma_commit(); PROFS(); QREL(); }
#define PUMP0() { PUMP1(); SCHED_FENCE(); }
#define WSTEP() { \
      const uint32_t s4 = (ub - bar_full - 256) >> 1; \
      const uint32_t da = dA0 + (((uint32_t)(WO_ASLOT(par) >> s4) & 15) << 10), db = dB0 + (((uint32_t)(WO_BSLOT >> s4) & 15) << 10); \
      mbar_wait(ub, par); \
      wgmma_fence(); \
      wgmma4_n128<1>(S1, da, db); \
      wgmma_commit(); PROFS(); \
      wgmma_wait<1>(); \
      if (s4) REL(ub + 376); \
      ub += 8; }
#define PUMPS(n) { _Pragma("unroll 1") for (int i_ = 0; i_ < (n); i_++) PUMP1(); }
#define LNSTEP(ACC, hh) { wgmma_fence(); wgmma_n192<1, 0>(ACC, make_desc(sbase + OFF_LNA + wg * 1024, 0, 128) ^ (1ull << 62), make_desc(sbase + OFF_LNB + (hh) * 4096, 0, 128) ^ (1ull << 62)); }
#define WARP_STORE(tm, tile, col, row) { fence_proxy_async_smem(); __syncwarp(); \
      if (elect_one()) { tma_store_2d(tm, (tile) + r0 * 128, col, (row) + r0); asm volatile("cp.async.bulk.commit_group;" ::: "memory"); } __syncwarp(); }
#define TILE_CONSTS(base, on, bit) \
      uint32_t ta[5]; \
      { PMASKS(on, bit); (void)pbit; ta[4] = pm0; } \
      _Pragma("unroll") for (int j = 0; j < 4; j++) ta[j] = (base) + srowoff + ((((uint32_t)j << 5) + lhi) ^ lsw); \
      PINU(ta, 5); SCHED_FENCE(); \
      const uint32_t pm0 = ta[4], pbit = (bit)
#define X_OUT(pc, W) { \
      _Pragma("unroll") for (int j = 0; j < 4; j++) \
        stsm_x4(ta[j] + (pc) * SLOT, \
                PBIT(pack_bf16((W)[j * 8 + 0], (W)[j * 8 + 1])), PBIT(pack_bf16((W)[j * 8 + 2], (W)[j * 8 + 3])), \
                (pack_bf16((W)[j * 8 + 4], (W)[j * 8 + 5])), (pack_bf16((W)[j * 8 + 6], (W)[j * 8 + 7]))); }
#define REST_P1(SKEW) { \
      mbar_wait(bar_stat2, par); \
      LNSTEP(S1, 1); \
      wgmma_commit(); \
      _Pragma("unroll 1") while (ub < bar_full + 256) { \
        const bool hold = ub == bar_full + 256 - 8 * (SKEW) && wg == 0; \
        if (hold) { wgmma_wait<0>(); REL(ub + 376); bar_sync<BAR_SKEW, 256>(); } \
        QSTEP(S1, RA_CUR, 1); \
        if (ub == bar_full + 248 && wg == 1) bar_arrive<BAR_SKEW, 256>(); \
        wgmma_wait<1>(); if (!hold) REL(ub + 376); ub += 8; \
      } \
      mbar_wait(bar_done + (31 - (SKEW)) * 8, par);        \
      wgmma_wait<0>(); \
      ACC_FENCE(S1, 96); \
      REL(bar_done + 31 * 8); \
      PROF(13); }
#define FOLD(tile, rd) { \
          LANE_CONSTS(); \
          float d[32]; \
          ACC_DEF(d, 32); \
          mbar_wait(bar_phi, 0); \
          wgmma_fence(); \
          _Pragma("unroll") for (int i = 0; i < 2; i++) { \
            const uint64_t da = make_desc((tile) + wg * 8192 + i * 64, 16, 1024); \
            const uint64_t db = make_desc(sbase + OFF_PHI + wg * 4096 + i * 2048, 16, 512) ^ (3ull << 62); \
            wgmma_n32<0>(d + i * 16, da, db); wgmma_n32<1>(d + i * 16, da + 2, db + 64); \
          } \
          wgmma_commit(); \
          PUMP0(); \
          ACC_FENCE(d, 32); \
          bar_wg(wg); \
          _Pragma("unroll") for (int i = 0; i < 4; i++) { \
            const float* x = d + (i & 1) * 8 + (i >> 1) * 2; \
            if (rd) sts128((tile) + wg * 8192 + ((warp & 3) * 16 + (i >> 1) * 8 + g) * 128 + (((2 * t + (i & 1)) ^ g) << 4), \
                           pack_bf16(x[0], x[1]), pack_bf16(x[4], x[5]), pack_bf16(x[16], x[17]), pack_bf16(x[20], x[21])); \
            else stsm_x4((tile) + srowoff + ((((uint32_t)i << 5) + lhi) ^ lsw), pack_bf16(d[i * 8], d[i * 8 + 1]), pack_bf16(d[i * 8 + 2], d[i * 8 + 3]), \
                         pack_bf16(d[i * 8 + 4], d[i * 8 + 5]), pack_bf16(d[i * 8 + 6], d[i * 8 + 7])); \
          } \
          }
#define XM_ISSUE() { mbar_wait(bar_xr, par); wgmma_fence(); \
      wgmma_copy(T_, dA0 + (OFF_RA >> 4), make_desc(sbase + OFF_ID, 128, 128) ^ (1ull << 62)); }
#define COPYN(d, s, n) _Pragma("unroll") for (int i_ = 0; i_ < (n); i_++) { uint32_t c_; asm volatile("mov.b32 %0, %1;" : "=r"(c_) : "f"((s)[i_])); (d)[i_] = __uint_as_float(c_); }
#define COPY64(d, s) COPYN(d, s, 64)
#define XM_DONE() { ACC_FENCE(T_, 64); COPY64(S1, T_); ACC_FENCE(S1, 64); \
      __syncwarp(); if (elect_one()) mbar_arrive_local(bar_lx); }
#define LOAD_X() { float T_[64]; ACC_DEF(T_, 64); wgmma_wait<0>(); XM_ISSUE(); wgmma_commit(); wgmma_wait<0>(); XM_DONE(); }

    float S0[96], S1[96];
#define FIRST_STEP(l_) { const int ln_ = (l_), l = ln_; const uint32_t ub = bar_full; (void)l; (void)ub; ACC_DEF(S0, 96); wgmma_fence(); wgmma4_n192<0>(S0, dA0 + (OFF_S >> 4), dB0); wgmma_commit(); PROFS(); }
    mbar_wait(bar_full, 0);
    FIRST_STEP(0);
    LOAD_EPOCH();
#pragma unroll 1
    for (int l = 0;; l++) {
      const uint32_t par = l & 1;
      uint32_t ub = bar_full + 8;
      PROF(1);
      {
        LANE_CONSTS();
        uint32_t ta[4];
#pragma unroll
        for (int j = 0; j < 4; j++) ta[j] = pK + srowoff + ((((uint32_t)j << 5) + lhi) ^ lsw);
        float p0, p1, a0 = 0.f, a1 = 0.f, q0 = 0.f, q1 = 0.f;
#define STATS(j0, j1) _Pragma("unroll") for (int j = (j0); j < (j1); j++) { \
          uint32_t x[4]; \
          ldsm_x4(ta[j & 3] + (j >> 2) * SLOT, x[0], x[1], x[2], x[3]); \
          if (j == 0) { p0 = __shfl_sync(0xffffffffu, bf_lo(x[0]), lane & 28); p1 = __shfl_sync(0xffffffffu, bf_lo(x[1]), lane & 28); } \
          _Pragma("unroll") for (int i = 0; i < 4; i += 2) { \
            const float d0 = bf_lo(x[i]) - p0, d1 = bf_hi(x[i]) - p0, d2 = bf_lo(x[i + 1]) - p1, d3 = bf_hi(x[i + 1]) - p1; \
            a0 += d0 + d1; a1 += d2 + d3; \
            q0 = fmaf(d1, d1, fmaf(d0, d0, q0)); q1 = fmaf(d3, d3, fmaf(d2, d2, q1)); } } \
          asm volatile("" : "+f"(a0), "+f"(a1), "+f"(q0), "+f"(q1), "+f"(p0), "+f"(p1)); SCHED_FENCE()
        if (SB0) { STATS(0, SB0); }
        bar_wg(wg);
        QSTEP(S0, dA0 + ((OFF_S + SLOT) >> 4), 1);
        QREL();
        SCHED_FENCE();
        STATS(SB0, SB1);
        ACC_DEF(S1, 96);
        QSTEP(S1, dA0 + (OFF_S >> 4), 0);
        QREL();
        SCHED_FENCE();
        STATS(SB1, SB2);
        QSTEP(S1, dA0 + ((OFF_S + SLOT) >> 4), 1);
        QREL();
        SCHED_FENCE();
        STATS(SB2, 8);
#pragma unroll
        for (int o = 1; o <= 2; o <<= 1) {
          a0 += __shfl_xor_sync(0xffffffffu, a0, o); a1 += __shfl_xor_sync(0xffffffffu, a1, o);
          q0 += __shfl_xor_sync(0xffffffffu, q0, o); q1 += __shfl_xor_sync(0xffffffffu, q1, o);
        }
        if (t == 1) { a0 = a1; q0 = q1; p0 = p1; }
        if (t < 2) st_b64(g_stats + (size_t)(mm * 128 + r0 + g + t * 8) * 8 + jj, __float_as_uint(fmaf(a0, 1.f / 128.f, p0)),
                          (__float_as_uint(fmaxf(fmaf(a0 * (-1.f / 128.f), a0, q0), 0.f)) & ~3u) | STAT_TAG(l));
        if (l) { asm volatile("cp.async.bulk.wait_group 0;" ::: "memory"); bar_arrive<BAR_X1, 288>(); }
#pragma unroll 1
        for (int i = 0; i < 14; i++) {
          QSTEP(S0, RA_CUR, 1);
          if (i == 0) PROF(2);
          QREL();
        }
      }
      LANE_CONSTS();
      mbar_wait(bar_stat, par);
      LNSTEP(S0, 0);
      wgmma_commit();
      const float rs0 = lds32f(sbase + OFF_ST + (r0 + g) * 4), rs1 = lds32f(sbase + OFF_ST + (r0 + g + 8) * 4);
      PUMP0();
      ACC_FENCE(S0, 96);
      PROF(3);
      if (!par) {
        constexpr uint32_t par = 0;
        uint32_t qa[16];
        uint32_t kf[24], vf[24];
#define DRAIN_A(ACC, hp, PMP) { \
          LANE_CONSTS(); \
          FRAG(kf, ACC + 32, 0, (hp) * 2); \
          PMP; \
          FRAG(vf, ACC + 64, 1, (hp) * 2 + 1); \
          _Pragma("unroll") for (int i_ = 0; i_ < 16; i_++) qa[i_] = pack_bf16(ACC[2 * i_], ACC[2 * i_ + 1]); \
          PINU(qa, 16); }
        DRAIN_A(S0, 0, PUMP0());
        if (l == 0 && NLAYERS > 1) {
#pragma unroll 1
          for (int rd = 1; rd >= 0; rd--) {
            FOLD(sbase + (12 - rd) * SLOT, rd);
            fence_proxy_async_smem();
            asm volatile("bar.arrive %0, 288;" :: "r"(BAR_WF + 1 - rd) : "memory");
          }
        }
        PUMPS(FPUMP);
        if (l == 0 && NLAYERS > 1) mbar_wait(bar_phi, 1);
#pragma unroll 1
        for (int h = 0; h < 2; h++) {
          PROFH(4, 16);
          LANE_CONSTS();
          FRAG_PUT(kf + 16, 10); FRAG_PUT(vf + 16, 11);
          STG_ARRIVE();
          if (h) { PROF(8); LOAD_X(); PROF(9); WSTEP(); PROF(10); } else PUMPS(HPUMP2);
          const bool gt0 = 2 * t > g, gt1 = 2 * t >= g;
          uint32_t msk[2] = {(gt0 ? 0xFFFFu : 0u) | (gt1 ? 0xFFFF0000u : 0u), g == 2 * t ? 0x10001u : 0u};
          PINU(msk, 2);
          TILE_CONSTS(sbase, false, 0);
          (void)pm0; (void)pbit;
          if (h) PROF(12);
          STG_WAIT();
          if (h) PROF(14);
          if (warp < 2) mbar_wait(bar_halo, h);
          if (h) PROF(15);
          if (h == 0) mbar_wait(ub, par);
          FRAG_GET(kf, 10);
          PROFH(5, 17);
          float s[2][3][4];
#pragma unroll
          for (int ks = 0; ks < 2; ks++)
#pragma unroll
            for (int i = 0; i < 6; i++) {
              const int hh = i & 1, jb = 2 - (i >> 1);
              const uint32_t* b = kf + jb * 8 + hh * 4 + ks * 2;
              if (ks) mma_bf16(s[hh][jb], qa[hh * 8 + 4], qa[hh * 8 + 5], qa[hh * 8 + 6], qa[hh * 8 + 7], b[0], b[1]);
              else mma_bf16_z(s[hh][jb], qa[hh * 8], qa[hh * 8 + 1], qa[hh * 8 + 2], qa[hh * 8 + 3], b[0], b[1]);
            }
          if (h == 0) PUMPN()
          PROFH(6, 18);
          float va[2][2], vb[2][2], mx[2][2];
#pragma unroll
          for (int hh = 0; hh < 2; hh++) {
            va[hh][0] = gt0 ? s[hh][0][0] : s[hh][1][0];
            vb[hh][0] = gt1 ? s[hh][0][1] : s[hh][1][1];
            va[hh][1] = gt0 ? s[hh][1][2] : s[hh][2][2];
            vb[hh][1] = gt1 ? s[hh][1][3] : s[hh][2][3];
          }
          if (warp < 2 && mm == 0) {
#pragma unroll
            for (int hh = 0; hh < 2; hh++) { if (gt0) va[hh][0] = -INFINITY; if (gt1) vb[hh][0] = -INFINITY; }
          }
#pragma unroll
          for (int i = 0; i < 4; i++) mx[i >> 1][i & 1] = fmaxf(va[i >> 1][i & 1], vb[i >> 1][i & 1]);
#pragma unroll
          for (int o = 1; o <= 2; o <<= 1)
#pragma unroll
            for (int i = 0; i < 4; i++) mx[i >> 1][i & 1] = fmaxf(mx[i >> 1][i & 1], __shfl_xor_sync(0xffffffffu, mx[i >> 1][i & 1], o));
          const float sc0 = rs0 * (0.17677669529663687f * LOG2E), sc1 = rs1 * (0.17677669529663687f * LOG2E);
#pragma unroll
          for (int i = 0; i < 4; i++) {
            const float sc = (i & 1) ? sc1 : sc0, m = mx[i >> 1][i & 1];
            va[i >> 1][i & 1] = ex2((va[i >> 1][i & 1] - m) * sc); vb[i >> 1][i & 1] = ex2((vb[i >> 1][i & 1] - m) * sc);
            mx[i >> 1][i & 1] = va[i >> 1][i & 1] + vb[i >> 1][i & 1];
          }
          if (h == 0) { PIN(&va[0][0], 4); PIN(&vb[0][0], 4); PIN(&mx[0][0], 4); PUMP1(); }
          if (h) PROF(20);
          if (warp < 2) mbar_wait(bar_halo + 8, h);
          if (h) PROF(21);
          if (h == 0) mbar_wait(ub, par);
          FRAG_GET(vf, 11);
#pragma unroll
          for (int o = 1; o <= 2; o <<= 1)
#pragma unroll
            for (int i = 0; i < 4; i++) mx[i >> 1][i & 1] += __shfl_xor_sync(0xffffffffu, mx[i >> 1][i & 1], o);
          float o[8][4];
          uint32_t pa[4][2];
#pragma unroll
          for (int i = 0; i < 4; i++) {
            const float iv = rcp_fast(mx[i >> 1][i & 1]);
            const uint32_t w = pack_bf16(va[i >> 1][i & 1] * iv, vb[i >> 1][i & 1] * iv);
            pa[i][0] = w & msk[0]; pa[i][1] = w & ~msk[0];
          }
          PROFH(7, 19);
#pragma unroll
          for (int i = 7; i >= 0; i--) {
            const uint32_t* a = vf + (i >> 2) * 8 + (i & 3) * 2;
            mma_bf16_z(o[i], a[0], a[1], a[8], a[9], pa[(i & 2) + (i >> 2)][0], pa[(i & 2) + (i >> 2)][1]);
          }
          if (h == 0) PUMPN() else mbar_wait(bar_done + 30 * 8, par);
          if (NLAYERS > 1 && l + h == 0) mbar_wait(bar_phi + 8, 0);
          if (h) PROF(22);
          {
            const uint32_t pm0 = msk[1], pbit = O_BIT(l) * 0x10001u;
#pragma unroll
            for (int i = 0; i < 4; i++)
              stsm_x4_t(ta[i] + (h ? 3 : 12) * SLOT, PBIT(pack_bf16(o[i][0], o[i][1])), PBIT(pack_bf16(o[i + 4][0], o[i + 4][1])),
                        pack_bf16(o[i][2], o[i][3]), pack_bf16(o[i + 4][2], o[i + 4][3]));
          }
          WARP_STORE(&tm_os, sbase + (h ? 3 : 12) * SLOT, jj * 128 + h * 64, mm * 128);
          PROFH(11, 23);
          if (h) break;
          REST_P1(ASKEW);
          asm volatile("cp.async.bulk.wait_group.read 0;" ::: "memory");
          DRAIN_A(S1, 1, {});
        }
      } else {
        constexpr uint32_t par = 1;
        float st[32];
        const float c0 = rs0 * LOG2E, c1 = rs1 * LOG2E;
        { V_ADDR(pV, 0); STAGE_V(S0 + 64); }
        if (warp < 2) sts128(sbase + OFF_ONES + warp * 512 + lane * 16, 0x3F803F80u, 0x3F803F80u, 0x3F803F80u, 0x3F803F80u);
        scale32(st, S0, c0, c1);
        PIN(st, 32);
#define PHI_PIECE(c) { \
          e_[2 * (c)] = ex2(st[2 * (c)]); e_[2 * (c) + 1] = ex2(st[2 * (c) + 1]); \
          _Pragma("unroll") for (int k_ = 4 * (c); k_ < 4 * (c) + 4; k_++) m_[(c) >> 1] = (k_ & 7) ? fmaf(st[k_], st[k_], m_[(c) >> 1]) : st[k_] * st[k_]; \
          asm volatile("" : "+f"(e_[2 * (c)]), "+f"(e_[2 * (c) + 1]), "+f"(m_[(c) >> 1])); SCHED_FENCE(); }
#define PHI_FIN() { \
          big = __any_sync(0xffffffffu, !(fmaxf(fmaxf(m_[0], m_[1]), fmaxf(m_[2], m_[3])) < BIGLIM)); \
          if (__builtin_expect(big, 0)) { COPYN(e_, st, 16); } \
          _Pragma("unroll") for (int k_ = 0; k_ < 16; k_++) st[k_] = e_[k_]; \
          PIN(st, 16); }
#define KV_MMA(vs, IL) { \
          const uint32_t dp = dA0 + 12 * 1024 - wg * 2560, dv = dA0 + (vs) * 1024 + ((OFF_ONES - (vs) * SLOT - 16) << 12) - wg * (512 << 16); \
          STG_WAIT(); \
          wgmma_fence(); \
          _Pragma("unroll") for (int ks = 0; ks < 8; ks++) { \
            const uint64_t a = DESC(dp + ks * 128, 0x40000040), b = DESC(dv + ks * (64 - (64 << 16)), 0x80000020); \
            if ((IL) && ks) wgmma_fence(); \
            if (ks == 0) wgmma_n40<0, 1>(kv, a, b); else wgmma_n40<1, 1>(kv, a, b); \
            if (ks == 7) wgmma_commit(); \
            if (IL) PHI_PIECE(ks); } }
#define KV_RED1(i) if (h) red_v4(g_kv[l >> 1] + (jj * 4) * KVH + warp * 768 + lane * 4 + (i) * 128, S0[32 + (i) * 3], S0[33 + (i) * 3], S0[34 + (i) * 3], 1.f)
#define KV_REDS(n) { _Pragma("unroll") for (int i_ = 0; i_ < 6; i_++) if (((RPACE >> (4 * i_)) & 15) == (n)) KV_RED1(i_); }
#define KV_SEND(kp) { \
          float sd[9]; \
          _Pragma("unroll") for (int i = 0; i < 8; i++) { (kp)[i] = kv[i]; sd[i] = kv[8 + i]; } \
          (kp)[8] = rank ? kv[18] : kv[16]; sd[8] = rank ? kv[16] : kv[18]; \
          const uint32_t ra = sbase + peer + (warp * 32 + lane) * 4, rb = bar_kx + peer; \
          if (elect_one()) mbar_expect_tx(bar_kx, 1152); \
          _Pragma("unroll") for (int i = 0; i < 2; i++) \
            asm volatile("st.async.weak.shared::cluster.mbarrier::complete_tx::bytes.v4.f32 [%0], {%1, %2, %3, %4}, [%5];" \
                         :: "r"(ra + (warp * 32 + lane) * 12 + OFF_PHI + i * 4096), "f"(sd[4 * i]), "f"(sd[4 * i + 1]), "f"(sd[4 * i + 2]), "f"(sd[4 * i + 3]), "r"(rb) : "memory"); \
          asm volatile("st.async.weak.shared::cluster.mbarrier::complete_tx::bytes.f32 [%0], %1, [%2];" :: "r"(ra + OFF_LNB), "f"(sd[8]), "r"(rb) : "memory"); }
#define KV_RECV(kp, hp) { \
          float r_[9]; \
          float* kvg = g_kv[l >> 1] + (jj * 4 + (hp) * 2) * KVH + warp * 768 + rank * 384 + lane * 4; \
          mbar_wait(bar_kx, l >> 1); \
          _Pragma("unroll") for (int i = 0; i < 2; i++) \
            asm volatile("ld.shared.v4.f32 {%0, %1, %2, %3}, [%4];" : "=f"(r_[4 * i]), "=f"(r_[4 * i + 1]), "=f"(r_[4 * i + 2]), "=f"(r_[4 * i + 3]) \
                         : "r"(sbase + OFF_PHI + i * 4096 + (warp * 32 + lane) * 16) : "memory"); \
          r_[8] = lds32f(sbase + OFF_LNB + (warp * 32 + lane) * 4); \
          _Pragma("unroll") for (int i = 0; i < 3; i++) red_v4(kvg + i * 128, (kp)[3 * i] + r_[3 * i], (kp)[3 * i + 1] + r_[3 * i + 1], (kp)[3 * i + 2] + r_[3 * i + 2], 2.f); }
#define KV_LOAD(hp) { \
          const uint4* kvg = reinterpret_cast<const uint4*>(g_kv[l >> 1] + (jj * 4 + (hp) * 2) * KVH) + warp * 192 + lane; \
          _Pragma("unroll") for (int i = 0; i < 6; i++) v[i] = ld_b128(kvg + i * 32); }
#define KVV(i) __uint_as_float((i) % 3 == 0 ? v[(i) / 3].x : ((i) % 3 == 1 ? v[(i) / 3].y : v[(i) / 3].z))
#define KV_TILE(hp) { \
          _Pragma("unroll 1") for (int it = 0; it < (1 << 16); it++) { \
            if (__all_sync(0xffffffffu, (v[0].w & v[1].w & v[2].w & v[3].w & v[4].w & v[5].w) == 0x41800000u)) break; \
            RETRY_COUNT(); \
            KV_LOAD(hp); \
          } \
          if (hp) PROF(26); else PROF(25); \
          const uint32_t e = lane & 7, jt = ((lane >> 1) & 4) + (e >> 1); \
          const uint32_t row = ((((warp >> 1) ^ wg) & 1) << 5) + ((jt & 1) << 4) + ((warp & 1) << 3) + (jt & 6) + (e & 1); \
          const uint32_t kd = pV + wg * 8192 + row * 128, ksw = (row & 7) << 4; \
          _Pragma("unroll") for (int i = 0; i < 2; i++) \
            stsm_x4(kd + ((i * 32 + lhi) ^ ksw), pack_bf16(KVV(i * 9), KVV(i * 9 + 1)), pack_bf16(KVV(i * 9 + 2), KVV(i * 9 + 3)), \
                    pack_bf16(KVV(i * 9 + 4), KVV(i * 9 + 5)), pack_bf16(KVV(i * 9 + 6), KVV(i * 9 + 7))); \
          stsm_x4(kd + ((64u + lhi) ^ ksw), pack_bf16(KVV(8), 1.f), pack_bf16(KVV(17), 1.f), 0u, 0u); }
#pragma unroll 1
        for (int h = 0; h < 2; h++) {
          PROFH(4, 6);
          PUMP0();
          LANE_CONSTS();
          const uint32_t dsw = (uint32_t)(g ^ (2 * t)) << 4, dst = ((t & 2) ? pK : sbase + 12 * SLOT) + (r0 + g) * 128;
          float e[16], f[16];
          KV_REDS(1);
          float sa = exps16_<0>(e, st);
          exps16_fix<0>(e, st, sa);
          asm volatile("" : "+f"(sa)); PIN(e, 16); PUMP0();
          if (h) STG_WAIT();
          KV_REDS(2);
          store16(e, sa, dst, dsw, 4);
          float sb = exps16_<1>(f, st);
          exps16_fix<1>(f, st, sb);
          asm volatile("" : "+f"(sb)); PIN(f, 16); PUMP0();
          KV_REDS(3);
          store16(f, sb, dst, dsw, 0);
          float sc = exps16_<0>(e, st + 2);
          exps16_fix<0>(e, st + 2, sc);
          asm volatile("" : "+f"(sc)); PIN(e, 16); PUMP0();
          KV_REDS(4);
          store16(e, sc, dst + 1024, dsw, 4);
          float sd = exps16_<1>(f, st + 2);
          exps16_fix<1>(f, st + 2, sd);
          asm volatile("" : "+f"(sd)); PIN(f, 16); PUMP0();
          store16(f, sd, dst + 1024, dsw, 0);
          PROFH(5, 7);
          if (h) break;
          {
            float kv[20];
            ACC_DEF(kv, 20);
            fence_proxy_async_smem();
            STG_ARRIVE();
            float e_[16], m_[4];
            KV_MMA(11, 0);
            PUMP0();
            ACC_FENCE(kv, 20);
            STG_ARRIVE();
            scale32(st, S0 + 32, c0, c1);
            PIN(st, 32);
            {
              COPYN(S0 + 32, kv, 8); COPYN(S0 + 40, kv + 16, 1); COPYN(S0 + 41, kv + 8, 8); COPYN(S0 + 49, kv + 18, 1);
              const int h = 1;
              KV_REDS(0);
            }
          }
        }
        bool big;
        uint4 v[6];
        {
          float kv[20];
          { LANE_CONSTS(); KV_LOAD(0); }
          mbar_wait(bar_stat2, par);
          ub = bar_full + 240;
          LNSTEP(S1, 1);
          PUMP1();
          if (wg == 0) bar_sync<BAR_SKEW, 256>();
          QSTEP(S1, RA_CUR, 1);
          if (wg == 1) bar_arrive<BAR_SKEW, 256>();
          QREL();
          { LANE_CONSTS(); KV_TILE(0); }
          LANE_CONSTS();
          V_ADDR(sbase + 3 * SLOT, rank * 32);
          PINU(va_, 2);
          mbar_wait(bar_done + 30 * 8, par);
          wgmma_wait<0>();
          ACC_FENCE(S1, 96);
          PROF(13);
          STAGE_V(S1 + 64);
          fence_proxy_async_smem();
          STG_ARRIVE();
          REL(bar_done + 31 * 8);
          scale32(st, S1, c0, c1);
          PIN(st, 32);
          PROF(16);
          ACC_DEF(kv, 20);
          float e_[16], m_[4];
          KV_MMA(3, 1);
          SCHED_FENCE();
          PROF(14);
          PHI_FIN();
          SCHED_FENCE();
          PROF(15);
          wgmma_wait<0>();
          ACC_FENCE(kv, 20);
          PROF(12);
          { float kp[9]; KV_SEND(kp); _Pragma("unroll") for (int i = 0; i < 3; i++) v[i] = make_uint4(__float_as_uint(kp[3 * i]), __float_as_uint(kp[3 * i + 1]), __float_as_uint(kp[3 * i + 2]), 0u); }
          PROF(17);
        }
#pragma unroll 1
        for (int h = 0; h < 2; h++) {
          const uint32_t pO = sbase + (h ? 3 : 8) * SLOT;
          LANE_CONSTS();
          uint32_t fq[32];
          PROFH(18, 32);
          SCHED_FENCE();
          phiq_b<1>(fq, st, big); PINU(fq, 16); PIN(st + 16, 16);
          SCHED_FENCE();
          PROFH(8, 9);
          if (h) {
            asm volatile("cp.async.bulk.wait_group.read 0;" ::: "memory");
            mbar_wait(bar_lx, par);
            PROF(30);
            KV_TILE(1);
            fence_proxy_async_smem();
            STG_ARRIVE();
          }
          SCHED_FENCE();
          if (h == 0) {
            float kp[9];
#pragma unroll
            for (int i = 0; i < 9; i++) kp[i] = KVV(i);
            KV_RECV(kp, 1);
            SCHED_FENCE();
          }
          phiq_b<0>(fq + 16, st + 16, big); PINU(fq + 16, 16);
          PROFH(10, 21);
          if (h) STG_WAIT();
          wgmma_wait<0>();
          ACC_FENCE(S1, 64);
          PROFH(19, 33);
          float o[4][20];
#define O_MMA(hh) { \
            const uint64_t db = make_desc(pV + (hh) * 8192, 16, 1024); \
            ACC_DEF(o[(hh) * 2], 20); ACC_DEF(o[(hh) * 2 + 1], 20); \
            wgmma_fence(); \
            wgmma_n40_rs<0>(o[(hh) * 2], fq + (hh) * 16, db + 256); wgmma_n40_rs<0>(o[(hh) * 2 + 1], fq + (hh) * 16 + 8, db); \
            wgmma_n40_rs<1>(o[(hh) * 2], fq + (hh) * 16 + 4, db + 384); wgmma_n40_rs<1>(o[(hh) * 2 + 1], fq + (hh) * 16 + 12, db + 128); \
            wgmma_commit(); }
          O_MMA(0);
          SCHED_FENCE();
          PMASKS(true, O_BIT(l));
#pragma unroll
          for (int hh = 0; hh < 2; hh++) {
            wgmma_wait<0>();
            ACC_FENCE(o[hh * 2], 20); ACC_FENCE(o[hh * 2 + 1], 20);
            if (!hh) { O_MMA(1); SCHED_FENCE(); }
            if (hh) PROFH(22, 24);
            const float* x = o[hh * 2];
            const float* y = o[hh * 2 + 1];
            const float sx0 = x[17] * 0x1p-40f, sy0 = y[17] * 0x1p-40f, sx1 = x[19] * 0x1p-40f, sy1 = y[19] * 0x1p-40f;
            const float i0 = rcp_fast(fmaf(fmaf(x[17], 1e-6f, x[16]), sy0, y[16] * sx0)), i1 = rcp_fast(fmaf(fmaf(x[19], 1e-6f, x[18]), sy1, y[18] * sx1));
            const float ax0 = sy0 * i0, ay0 = sx0 * i0, ax1 = sy1 * i1, ay1 = sx1 * i1;
#pragma unroll
            for (int dp = 0; dp < 2; dp++)
              stsm_x4(pO + srowoff + ((hh * 64 + dp * 32 + lhi) ^ lsw),
                      PBIT(pack_bf16(fmaf(x[dp * 8], ax0, y[dp * 8] * ay0), fmaf(x[dp * 8 + 1], ax0, y[dp * 8 + 1] * ay0))),
                      PBIT(pack_bf16(fmaf(x[dp * 8 + 2], ax1, y[dp * 8 + 2] * ay1), fmaf(x[dp * 8 + 3], ax1, y[dp * 8 + 3] * ay1))),
                      (pack_bf16(fmaf(x[dp * 8 + 4], ax0, y[dp * 8 + 4] * ay0), fmaf(x[dp * 8 + 5], ax0, y[dp * 8 + 5] * ay0))),
                      (pack_bf16(fmaf(x[dp * 8 + 6], ax1, y[dp * 8 + 6] * ay1), fmaf(x[dp * 8 + 7], ax1, y[dp * 8 + 7] * ay1))));
          }
          WARP_STORE(&tm_os, pO, jj * 128 + h * 64, mm * 128);
          PROFH(20, 34);
          if (h) break;
          float T_[64];
          scale32(st, S1 + 32, c0, c1);
          PIN(st, 32);
          ACC_DEF(T_, 64);
          XM_ISSUE(); wgmma_commit();
          SCHED_FENCE();
          big = any_big(st);
          SCHED_FENCE();
          PROF(27);
          wgmma_wait<0>(); XM_DONE();
          PROF(28);
          bar_wg(wg);
          WSTEP();
          SCHED_FENCE();
          PROF(29);
          KV_LOAD(1);
          phiq_a(st, big); PIN(st, 16);
          PROF(31);
        }
      }
      __syncwarp();
      if (elect_one()) mbar_arrive_local(bar_epi);
      bar_wg(wg);
#pragma unroll 1
      while (ub < bar_full + 384) {
        WSTEP();
        if (ub == bar_full + 8 * 41) { asm volatile("cp.async.bulk.wait_group.read 0;" ::: "memory"); PROF(35); }
        if (ub == bar_full + 8 * 42) PROF(36);
      }
      {
        float Wb[32];
        LANE_CONSTS();
        TILE_CONSTS(pK, l < NLAYERS - 1, X_BIT(l));
        if (l < NLAYERS - 1) mbar_wait(bar_full, par ^ 1);
        wgmma_wait<0>();
        ACC_FENCE(S1, 64);
        COPYN(Wb, S1 + 32, 32);
        PROF(37);
        X_OUT(0, S1);
        WARP_STORE(l < NLAYERS - 1 ? &tm_os : &tm_xo, pK, jj * 128 + (l < NLAYERS - 1 ? 0 : (warp & 1) * 1024), l < NLAYERS - 1 ? mm * 128 + S_LEN : mm * 64 + (warp >> 1) * 16 - r0);
        if (l == NLAYERS - 1) { PMASKS(false, 0); X_OUT(1, Wb); break; }
        PROF(38);
        bar_wg(wg);
        FIRST_STEP(l + 1);
        REL(bar_done + 47 * 8);
        PROF(39);
        { PMASKS(false, 0); X_OUT(1, Wb); }
        fence_proxy_async_smem();
      }
    }
    WARP_STORE(&tm_xo, pV, jj * 128 + 64 + (warp & 1) * 1024, mm * 64 + (warp >> 1) * 16 - r0);
    asm volatile("cp.async.bulk.wait_group.read 0;" ::: "memory");
    cluster_sync();
  }
}

typedef CUresult (*PFN_encode)(CUtensorMap*, CUtensorMapDataType, cuuint32_t, void*, const cuuint64_t*, const cuuint64_t*,
                               const cuuint32_t*, const cuuint32_t*, CUtensorMapInterleave, CUtensorMapSwizzle,
                               CUtensorMapL2promotion, CUtensorMapFloatOOBfill);

CUtensorMap make_map(PFN_encode enc, const void* ptr, uint64_t inner, uint64_t outer, uint32_t box_inner, uint32_t box_outer,
                     CUtensorMapSwizzle swz = CU_TENSOR_MAP_SWIZZLE_128B, int promo = CU_TENSOR_MAP_L2_PROMOTION_L2_256B) {
  CUtensorMap m;
  cuuint64_t dims[2] = {inner, outer};
  cuuint64_t strides[1] = {inner * 2};
  cuuint32_t box[2] = {box_inner, box_outer};
  cuuint32_t es[2] = {1, 1};
  enc(&m, CU_TENSOR_MAP_DATA_TYPE_BFLOAT16, 2, const_cast<void*>(ptr), dims, strides, box, es, CU_TENSOR_MAP_INTERLEAVE_NONE,
      swz, (CUtensorMapL2promotion)promo, CU_TENSOR_MAP_FLOAT_OOB_FILL_NONE);
  return m;
}

CUtensorMap make_tile_map(PFN_encode enc, const void* ptr, uint64_t rows, bool by_parity, int promo) {
  CUtensorMap m;
  cuuint64_t dims[4] = {D_MODEL, 16, 2, rows / 32};
  cuuint64_t strides[3] = {by_parity ? 4096u : 2048u, by_parity ? 2048u : 32768u, 65536};
  cuuint32_t box[4] = {64, 16, 2, 4};
  cuuint32_t es[4] = {1, 1, 1, 1};
  enc(&m, CU_TENSOR_MAP_DATA_TYPE_BFLOAT16, 4, const_cast<void*>(ptr), dims, strides, box, es, CU_TENSOR_MAP_INTERLEAVE_NONE,
      CU_TENSOR_MAP_SWIZZLE_128B, (CUtensorMapL2promotion)promo, CU_TENSOR_MAP_FLOAT_OOB_FILL_NONE);
  return m;
}

}

extern "C" void kernel_launch(void* const* d_in, const int* in_sizes, int n_in, void* d_out, int out_size) {
  (void)in_sizes; (void)n_in; (void)out_size;
  static PFN_encode enc = nullptr;
  if (!enc) {
    void* fn = nullptr;
    cudaDriverEntryPointQueryResult qr;
    cudaGetDriverEntryPoint("cuTensorMapEncodeTiled", &fn, cudaEnableDefault, &qr);
    enc = (PFN_encode)fn;
    cudaFuncSetAttribute(mega_kernel, cudaFuncAttributeMaxDynamicSharedMemorySize, SMEM_BYTES);
  }
  Params prm;
  prm.x0 = (const __nv_bfloat16*)d_in[0];
  prm.wA_qkv = (const __nv_bfloat16*)d_in[1];
  prm.wA_o = (const __nv_bfloat16*)d_in[2];
  prm.wB_qkv = (const __nv_bfloat16*)d_in[4];
  prm.wB_phi = (const __nv_bfloat16*)d_in[5];
  prm.wB_o = (const __nv_bfloat16*)d_in[6];
  prm.out = (__nv_bfloat16*)d_out;
  void *obuf = nullptr, *wf = nullptr;
  cudaGetSymbolAddress(&obuf, g_obuf);
  cudaGetSymbolAddress(&wf, g_wfold);
  CUtensorMap tm_x0 = make_tile_map(enc, d_in[0], S_LEN, true, XPROMO);
  CUtensorMap tm_xo = make_map(enc, d_out, 2 * D_MODEL, S_LEN / 2, 64, 16);
  CUtensorMap tm_os = make_map(enc, obuf, D_MODEL, 2 * S_LEN, 64, 16);
  CUtensorMap tm_o = make_tile_map(enc, obuf, 2 * S_LEN, false, OPROMO);
  CUtensorMap tm_wf = make_map(enc, wf, 2048, D_MODEL, 64, 32);
  CUtensorMap tm_wqA = make_map(enc, d_in[1], 3 * D_MODEL, D_MODEL, 64, 32, CU_TENSOR_MAP_SWIZZLE_128B, WPROMO);
  CUtensorMap tm_wqB = make_map(enc, prm.wB_qkv, 3 * D_MODEL, D_MODEL, 64, 32);
  CUtensorMap tm_woA = make_map(enc, prm.wA_o, D_MODEL, D_MODEL, 64, 64);
  CUtensorMap tm_woB = make_map(enc, prm.wB_o, D_MODEL, D_MODEL, 64, 64);
  CUtensorMap tm_phi = make_map(enc, prm.wB_phi, 32, 1024, 32, 128, CU_TENSOR_MAP_SWIZZLE_64B);
  mega_kernel<<<NMAIN + NAUX, 384, SMEM_BYTES>>>(tm_x0, tm_xo, tm_os, tm_o, tm_wf, tm_wqA, tm_wqB, tm_woA, tm_woB, tm_phi, prm);
}
```

```cpp
#include <cuda_runtime.h>
#include <cuda.h>
#include <cuda_bf16.h>
#include <stdint.h>

#define NLAYERS 4

#define HPUMP2 1
#define ASKEW 2
#define FPUMP 3
#define PFGAP 100
#define POLLGAP 120
#define HW1 29
#define XPACE 0x06050401000000ull
#define XP0 4
#define HW0 18
#define XD 4
#define WFGAP 50
#define EARLY 2
#define BIGLIM 3600.f
#define SUMLO 0x1p-100f
#define SUMHI 0x1p100f
#define XPROMO 2
#define OPROMO 3
#define STAG2 300
#define WPROMO 3
#define SB0 2
#define SB1 4
#define SB2 6
#define PROWS 3
#define SPD0 0
#define SPD1 0
#define SPD2 300
#define FRB 0x3535353535ull
#define NOB 0xFFFFFF00u
#define NO1 ~0u
#define NOX ~0u
#define FD0 0
#define FD1 3
#define RPACE 0x221100
namespace {

constexpr int S_LEN = 2048, D_MODEL = 1024;
constexpr int NAUX = 4, NMAIN = 128;
constexpr int SLOT = 16384;
constexpr int QST = 24576;
constexpr int OFF_RA = 6 * SLOT, OFF_S = 10 * SLOT;
constexpr int OFF_HALO = 13 * SLOT, OFF_LNB = OFF_HALO  , OFF_ONES = OFF_HALO + 3072;
constexpr int OFF_ST = OFF_HALO + 7168  , OFF_ID = OFF_HALO + 7680, OFF_PHI = OFF_HALO + 8192;
constexpr int OFF_BAR = 14 * SLOT;
constexpr int OFF_LNA = OFF_BAR + 1024;
constexpr int SMEM_BYTES = OFF_LNA + 2048;
#define WO_ASLOT(par) ((par) ? 0x9876CAB39876CA98ull : 0xBC7698A3BC7698BCull)
constexpr unsigned long long WO_BSLOT = 0x5432105421054210ull;
__device__ __forceinline__ int srcb(int j, int i) { return (i + (i >= j)) & 7; }
__device__ __forceinline__ int kslice(int j, int i) { return i < 2 ? 2 * j + i : (i < 9 ? 2 * srcb(j, i - 2) : 2 * srcb(j, i - 9) + 1); }
__device__ __forceinline__ int wslice(int j, int s) { return 2 * ((s & 7) ? srcb(j, (s & 7) - 1) : j) + (s >> 3); }
constexpr int KVH = 6 * 128 * 4;

struct __align__(128) Flag { unsigned v; unsigned pad[31]; };
struct Flags {
  Flag xready[4][16];
  Flag wfready[8];
  Flag done;
  Flag epoch;
};

__device__ Flags g_flags;
__device__ __nv_bfloat16 g_obuf[2 * S_LEN * D_MODEL];
#define O_BIT(l) ((epoch * NLAYERS + (l) + 1) & 1u)
#define X_BIT(l) ((epoch * (NLAYERS - 1) + (l) + 1) & 1u)
__device__ __nv_bfloat16 g_wfold[D_MODEL * 2048];
__device__ uint4 g_halo[16 * 8 * 512];
__device__ __align__(128) float g_kv[2][32 * KVH];
__device__ __align__(128) uint2 g_colsum[2][1536][2];
__device__ __align__(128) uint2 g_stats[S_LEN * 8];
#define H_BIT(l) (NLAYERS > 2 ? (uint32_t)((l) == 0) : (ep1 & 1))
#define STAT_TAG(l) ((ep1 * NLAYERS + (l) + 1) & 3u)

#define RETRY_COUNT()
#define PRL 0
#define PRU 0
#define PROFL 1
#define PROFW 0
#define PROFT(i) do {} while (0)
#define PROF(i) do {} while (0)
#define PROFH(i, j) do {} while (0)

__device__ __forceinline__ uint32_t smem_u32(const void* p) { return (uint32_t)__cvta_generic_to_shared(p); }
__device__ __forceinline__ bool elect_one() {
  uint32_t p;
  asm volatile("{\n.reg .pred p;\nelect.sync _|p, 0xffffffff;\nselp.u32 %0, 1, 0, p;\n}\n" : "=r"(p));
  return p != 0;
}
__device__ __forceinline__ void mbar_init(uint32_t bar, uint32_t cnt) {
  asm volatile("mbarrier.init.shared::cta.b64 [%0], %1;" :: "r"(bar), "r"(cnt));
}
__device__ __forceinline__ void mbar_expect_tx(uint32_t bar, uint32_t bytes) {
  asm volatile("mbarrier.arrive.expect_tx.shared::cta.b64 _, [%0], %1;" :: "r"(bar), "r"(bytes) : "memory");
}
#define mbar_wait(bar, parity) \
  asm volatile("{\n.reg .pred p, q;\nW_%=:\nmbarrier.try_wait.parity.shared::cta.b64 p, [%1], %2;\nadd.s32 %0, %0, -1;\n" \
               "setp.gt.and.s32 q, %0, 0, !p;\n@q bra.uni W_%=;\n}\n" : "+r"(budget) : "r"((uint32_t)(bar)), "r"((uint32_t)(parity)) : "memory")
#define mbar_wait_sl(bar, parity) \
  asm volatile("{\n.reg .pred p, q;\nW_%=:\nmbarrier.try_wait.parity.shared::cta.b64 p, [%1], %2, 20000;\nadd.s32 %0, %0, -64;\n" \
               "setp.gt.and.s32 q, %0, 0, !p;\n@q bra.uni W_%=;\n}\n" : "+r"(budget) : "r"((uint32_t)(bar)), "r"((uint32_t)(parity)) : "memory")
__device__ __forceinline__ void mbar_arrive_local(uint32_t bar) {
  asm volatile("mbarrier.arrive.shared::cta.b64 _, [%0];" :: "r"(bar) : "memory");
}
__device__ __forceinline__ void tma_load_2d(uint32_t dst, const CUtensorMap* tm, uint32_t bar, int c0, int c1) {
  asm volatile("cp.async.bulk.tensor.2d.shared::cluster.global.mbarrier::complete_tx::bytes [%0], [%1, {%3, %4}], [%2];"
               :: "r"(dst), "l"(tm), "r"(bar), "r"(c0), "r"(c1) : "memory");
}
__device__ __forceinline__ void tma_load_2d_mc(uint32_t dst, const CUtensorMap* tm, uint32_t bar, int c0, int c1) {
  asm volatile("cp.async.bulk.tensor.2d.shared::cluster.global.mbarrier::complete_tx::bytes.multicast::cluster [%0], [%1, {%3, %4}], [%2], %5;"
               :: "r"(dst), "l"(tm), "r"(bar), "r"(c0), "r"(c1), "h"((uint16_t)3) : "memory");
}
__device__ __forceinline__ void tma_store_2d(const CUtensorMap* tm, uint32_t src, int c0, int c1) {
  asm volatile("cp.async.bulk.tensor.2d.global.shared::cta.bulk_group [%0, {%2, %3}], [%1];"
               :: "l"(tm), "r"(src), "r"(c0), "r"(c1) : "memory");
}
__device__ __forceinline__ void tma_load_t(uint32_t dst, const CUtensorMap* tm, uint32_t bar, int c0, int row) {
  asm volatile("cp.async.bulk.tensor.4d.shared::cluster.global.mbarrier::complete_tx::bytes [%0], [%1, {%3, %5, %5, %4}], [%2];"
               :: "r"(dst), "l"(tm), "r"(bar), "r"(c0), "r"(row >> 5), "r"(0) : "memory");
}
__device__ __forceinline__ void tma_store_t(const CUtensorMap* tm, uint32_t src, int c0, int row) {
  asm volatile("cp.async.bulk.tensor.4d.global.shared::cta.bulk_group [%0, {%2, %4, %4, %3}], [%1];"
               :: "l"(tm), "r"(src), "r"(c0), "r"(row >> 5), "r"(0) : "memory");
}
__device__ __forceinline__ void bulk_commit_wait() {
  asm volatile("cp.async.bulk.commit_group;\ncp.async.bulk.wait_group 0;" ::: "memory");
}
__device__ __forceinline__ void prefetch_tmap(const CUtensorMap* tm) {
  asm volatile("prefetch.tensormap [%0];" :: "l"(tm) : "memory");
}
__device__ __forceinline__ void fence_proxy_async_global() { asm volatile("fence.proxy.async.global;" ::: "memory"); }
__device__ __forceinline__ void fence_proxy_async_smem() { asm volatile("fence.proxy.async.shared::cta;" ::: "memory"); }
__device__ __forceinline__ unsigned ld_relaxed(const unsigned* p) {
  unsigned v;
  asm volatile("ld.relaxed.gpu.global.u32 %0, [%1];" : "=r"(v) : "l"(p) : "memory");
  return v;
}
__device__ __forceinline__ void fence_acquire() { asm volatile("fence.acquire.gpu;" ::: "memory"); }
__device__ __forceinline__ void wait_flag(const unsigned* p, unsigned target) {
  int it = 0;
  while ((int)(ld_relaxed(p) - target) < 0 && ++it < (1 << 20)) {}
  fence_acquire();
}
__device__ __forceinline__ void signal_release(unsigned* p) {
  asm volatile("red.release.gpu.global.add.u32 [%0], 1;" :: "l"(p) : "memory");
}
template <int ID, int N> __device__ __forceinline__ void bar_arrive() { asm volatile("bar.arrive %0, %1;" :: "n"(ID), "n"(N) : "memory"); }
template <int ID, int N> __device__ __forceinline__ void bar_sync() { asm volatile("bar.sync %0, %1;" :: "n"(ID), "n"(N) : "memory"); }
__device__ __forceinline__ void bar_wg(int wg) { asm volatile("bar.sync %0, 128;" :: "r"(2 + wg) : "memory"); }
__device__ __forceinline__ void cluster_sync() {
  asm volatile("barrier.cluster.arrive.relaxed.aligned;\nbarrier.cluster.wait.aligned;" ::: "memory");
}
__device__ __forceinline__ void cluster_wait() { asm volatile("barrier.cluster.wait.acquire.aligned;" ::: "memory"); }
enum { BAR_X1 = 7, BAR_WF = 8  , BAR_SKEW = 10 };

__device__ __forceinline__ void wgmma_fence() { asm volatile("wgmma.fence.sync.aligned;" ::: "memory"); }
__device__ __forceinline__ void wgmma_commit() { asm volatile("wgmma.commit_group.sync.aligned;" ::: "memory"); }
template <int N> __device__ __forceinline__ void wgmma_wait() { asm volatile("wgmma.wait_group.sync.aligned %0;" :: "n"(N) : "memory"); }

template <int scale_d, int tnsp_b = 1> __device__ __forceinline__ void wgmma_n192(float* d, uint64_t descA, uint64_t descB) {
  asm volatile("{\n.reg .pred p;\nsetp.ne.b32 p, %98, 0;\n"
               "wgmma.mma_async.sync.aligned.m64n192k16.f32.bf16.bf16 {%0,%1,%2,%3,%4,%5,%6,%7,%8,%9,%10,%11,%12,%13,%14,%15,%16,%17,%18,%19,%20,%21,%22,%23,%24,%25,%26,%27,%28,%29,%30,%31,%32,%33,%34,%35,%36,%37,%38,%39,%40,%41,%42,%43,%44,%45,%46,%47,%48,%49,%50,%51,%52,%53,%54,%55,%56,%57,%58,%59,%60,%61,%62,%63,%64,%65,%66,%67,%68,%69,%70,%71,%72,%73,%74,%75,%76,%77,%78,%79,%80,%81,%82,%83,%84,%85,%86,%87,%88,%89,%90,%91,%92,%93,%94,%95}, %96, %97, p, 1, 1, 0, %99;\n}\n"
               : "+f"(d[0]), "+f"(d[1]), "+f"(d[2]), "+f"(d[3]), "+f"(d[4]), "+f"(d[5]), "+f"(d[6]), "+f"(d[7]), "+f"(d[8]), "+f"(d[9]), "+f"(d[10]), "+f"(d[11]), "+f"(d[12]), "+f"(d[13]), "+f"(d[14]), "+f"(d[15]), "+f"(d[16]), "+f"(d[17]), "+f"(d[18]), "+f"(d[19]), "+f"(d[20]), "+f"(d[21]), "+f"(d[22]), "+f"(d[23]), "+f"(d[24]), "+f"(d[25]), "+f"(d[26]), "+f"(d[27]), "+f"(d[28]), "+f"(d[29]), "+f"(d[30]), "+f"(d[31]), "+f"(d[32]), "+f"(d[33]), "+f"(d[34]), "+f"(d[35]), "+f"(d[36]), "+f"(d[37]), "+f"(d[38]), "+f"(d[39]), "+f"(d[40]), "+f"(d[41]), "+f"(d[42]), "+f"(d[43]), "+f"(d[44]), "+f"(d[45]), "+f"(d[46]), "+f"(d[47]), "+f"(d[48]), "+f"(d[49]), "+f"(d[50]), "+f"(d[51]), "+f"(d[52]), "+f"(d[53]), "+f"(d[54]), "+f"(d[55]), "+f"(d[56]), "+f"(d[57]), "+f"(d[58]), "+f"(d[59]), "+f"(d[60]), "+f"(d[61]), "+f"(d[62]), "+f"(d[63]), "+f"(d[64]), "+f"(d[65]), "+f"(d[66]), "+f"(d[67]), "+f"(d[68]), "+f"(d[69]), "+f"(d[70]), "+f"(d[71]), "+f"(d[72]), "+f"(d[73]), "+f"(d[74]), "+f"(d[75]), "+f"(d[76]), "+f"(d[77]), "+f"(d[78]), "+f"(d[79]), "+f"(d[80]), "+f"(d[81]), "+f"(d[82]), "+f"(d[83]), "+f"(d[84]), "+f"(d[85]), "+f"(d[86]), "+f"(d[87]), "+f"(d[88]), "+f"(d[89]), "+f"(d[90]), "+f"(d[91]), "+f"(d[92]), "+f"(d[93]), "+f"(d[94]), "+f"(d[95])
               : "l"(descA), "l"(descB), "n"(scale_d), "n"(tnsp_b));
}
template <int scale_d> __device__ __forceinline__ void wgmma4_n192(float* d, uint32_t da, uint32_t db) {
#define R_ "{%0,%1,%2,%3,%4,%5,%6,%7,%8,%9,%10,%11,%12,%13,%14,%15,%16,%17,%18,%19,%20,%21,%22,%23,%24,%25,%26,%27,%28,%29,%30,%31,%32,%33,%34,%35,%36,%37,%38,%39,%40,%41,%42,%43,%44,%45,%46,%47,%48,%49,%50,%51,%52,%53,%54,%55,%56,%57,%58,%59,%60,%61,%62,%63,%64,%65,%66,%67,%68,%69,%70,%71,%72,%73,%74,%75,%76,%77,%78,%79,%80,%81,%82,%83,%84,%85,%86,%87,%88,%89,%90,%91,%92,%93,%94,%95}"
  asm volatile("{\n.reg .pred p, q;\n.reg .b64 a, b;\nsetp.ne.b32 p, %98, 0;\nsetp.eq.b32 q, 0, 0;\nmov.b64 a, {%96, 0x40000040};\nmov.b64 b, {%97, 0x40000040};\n"
               "wgmma.mma_async.sync.aligned.m64n192k16.f32.bf16.bf16 " R_ ", a, b, p, 1, 1, 0, 1;\nadd.s64 a, a, 2;\nadd.s64 b, b, 128;\n"
               "wgmma.mma_async.sync.aligned.m64n192k16.f32.bf16.bf16 " R_ ", a, b, q, 1, 1, 0, 1;\nadd.s64 a, a, 2;\nadd.s64 b, b, 128;\n"
               "wgmma.mma_async.sync.aligned.m64n192k16.f32.bf16.bf16 " R_ ", a, b, q, 1, 1, 0, 1;\nadd.s64 a, a, 2;\nadd.s64 b, b, 128;\n"
               "wgmma.mma_async.sync.aligned.m64n192k16.f32.bf16.bf16 " R_ ", a, b, q, 1, 1, 0, 1;\n}\n"
               : "+f"(d[0]), "+f"(d[1]), "+f"(d[2]), "+f"(d[3]), "+f"(d[4]), "+f"(d[5]), "+f"(d[6]), "+f"(d[7]), "+f"(d[8]), "+f"(d[9]), "+f"(d[10]), "+f"(d[11]), "+f"(d[12]), "+f"(d[13]), "+f"(d[14]), "+f"(d[15]), "+f"(d[16]), "+f"(d[17]), "+f"(d[18]), "+f"(d[19]), "+f"(d[20]), "+f"(d[21]), "+f"(d[22]), "+f"(d[23]), "+f"(d[24]), "+f"(d[25]), "+f"(d[26]), "+f"(d[27]), "+f"(d[28]), "+f"(d[29]), "+f"(d[30]), "+f"(d[31]), "+f"(d[32]), "+f"(d[33]), "+f"(d[34]), "+f"(d[35]), "+f"(d[36]), "+f"(d[37]), "+f"(d[38]), "+f"(d[39]), "+f"(d[40]), "+f"(d[41]), "+f"(d[42]), "+f"(d[43]), "+f"(d[44]), "+f"(d[45]), "+f"(d[46]), "+f"(d[47]), "+f"(d[48]), "+f"(d[49]), "+f"(d[50]), "+f"(d[51]), "+f"(d[52]), "+f"(d[53]), "+f"(d[54]), "+f"(d[55]), "+f"(d[56]), "+f"(d[57]), "+f"(d[58]), "+f"(d[59]), "+f"(d[60]), "+f"(d[61]), "+f"(d[62]), "+f"(d[63]), "+f"(d[64]), "+f"(d[65]), "+f"(d[66]), "+f"(d[67]), "+f"(d[68]), "+f"(d[69]), "+f"(d[70]), "+f"(d[71]), "+f"(d[72]), "+f"(d[73]), "+f"(d[74]), "+f"(d[75]), "+f"(d[76]), "+f"(d[77]), "+f"(d[78]), "+f"(d[79]), "+f"(d[80]), "+f"(d[81]), "+f"(d[82]), "+f"(d[83]), "+f"(d[84]), "+f"(d[85]), "+f"(d[86]), "+f"(d[87]), "+f"(d[88]), "+f"(d[89]), "+f"(d[90]), "+f"(d[91]), "+f"(d[92]), "+f"(d[93]), "+f"(d[94]), "+f"(d[95])
               : "r"(da), "r"(db), "n"(scale_d));
#undef R_
}
template <int scale_d> __device__ __forceinline__ void wgmma4_n128(float* d, uint32_t da, uint32_t db) {
#define R_ "{%0,%1,%2,%3,%4,%5,%6,%7,%8,%9,%10,%11,%12,%13,%14,%15,%16,%17,%18,%19,%20,%21,%22,%23,%24,%25,%26,%27,%28,%29,%30,%31,%32,%33,%34,%35,%36,%37,%38,%39,%40,%41,%42,%43,%44,%45,%46,%47,%48,%49,%50,%51,%52,%53,%54,%55,%56,%57,%58,%59,%60,%61,%62,%63}"
  asm volatile("{\n.reg .pred p, q;\n.reg .b64 a, b;\nsetp.ne.b32 p, %66, 0;\nsetp.eq.b32 q, 0, 0;\nmov.b64 a, {%64, 0x40000040};\nmov.b64 b, {%65, 0x40000040};\n"
               "wgmma.mma_async.sync.aligned.m64n128k16.f32.bf16.bf16 " R_ ", a, b, p, 1, 1, 0, 1;\nadd.s64 a, a, 2;\nadd.s64 b, b, 128;\n"
               "wgmma.mma_async.sync.aligned.m64n128k16.f32.bf16.bf16 " R_ ", a, b, q, 1, 1, 0, 1;\nadd.s64 a, a, 2;\nadd.s64 b, b, 128;\n"
               "wgmma.mma_async.sync.aligned.m64n128k16.f32.bf16.bf16 " R_ ", a, b, q, 1, 1, 0, 1;\nadd.s64 a, a, 2;\nadd.s64 b, b, 128;\n"
               "wgmma.mma_async.sync.aligned.m64n128k16.f32.bf16.bf16 " R_ ", a, b, q, 1, 1, 0, 1;\n}\n"
               : "+f"(d[0]), "+f"(d[1]), "+f"(d[2]), "+f"(d[3]), "+f"(d[4]), "+f"(d[5]), "+f"(d[6]), "+f"(d[7]), "+f"(d[8]), "+f"(d[9]), "+f"(d[10]), "+f"(d[11]), "+f"(d[12]), "+f"(d[13]), "+f"(d[14]), "+f"(d[15]), "+f"(d[16]), "+f"(d[17]), "+f"(d[18]), "+f"(d[19]), "+f"(d[20]), "+f"(d[21]), "+f"(d[22]), "+f"(d[23]), "+f"(d[24]), "+f"(d[25]), "+f"(d[26]), "+f"(d[27]), "+f"(d[28]), "+f"(d[29]), "+f"(d[30]), "+f"(d[31]), "+f"(d[32]), "+f"(d[33]), "+f"(d[34]), "+f"(d[35]), "+f"(d[36]), "+f"(d[37]), "+f"(d[38]), "+f"(d[39]), "+f"(d[40]), "+f"(d[41]), "+f"(d[42]), "+f"(d[43]), "+f"(d[44]), "+f"(d[45]), "+f"(d[46]), "+f"(d[47]), "+f"(d[48]), "+f"(d[49]), "+f"(d[50]), "+f"(d[51]), "+f"(d[52]), "+f"(d[53]), "+f"(d[54]), "+f"(d[55]), "+f"(d[56]), "+f"(d[57]), "+f"(d[58]), "+f"(d[59]), "+f"(d[60]), "+f"(d[61]), "+f"(d[62]), "+f"(d[63])
               : "r"(da), "r"(db), "n"(scale_d));
#undef R_
}
template <int scale_d> __device__ __forceinline__ void wgmma_n32(float* d, uint64_t descA, uint64_t descB) {
  asm volatile("{\n.reg .pred p;\nsetp.ne.b32 p, %18, 0;\n"
               "wgmma.mma_async.sync.aligned.m64n32k16.f32.bf16.bf16 {%0,%1,%2,%3,%4,%5,%6,%7,%8,%9,%10,%11,%12,%13,%14,%15}, %16, %17, p, 1, 1, 0, 1;\n}\n"
               : "+f"(d[0]), "+f"(d[1]), "+f"(d[2]), "+f"(d[3]), "+f"(d[4]), "+f"(d[5]), "+f"(d[6]), "+f"(d[7]), "+f"(d[8]), "+f"(d[9]), "+f"(d[10]), "+f"(d[11]), "+f"(d[12]), "+f"(d[13]), "+f"(d[14]), "+f"(d[15])
               : "l"(descA), "l"(descB), "n"(scale_d));
}
template <int scale_d, int tnsp_a> __device__ __forceinline__ void wgmma_n40(float* d, uint64_t descA, uint64_t descB) {
  asm volatile("{\n.reg .pred p;\nsetp.ne.b32 p, %22, 0;\n"
               "wgmma.mma_async.sync.aligned.m64n40k16.f32.bf16.bf16 {%0,%1,%2,%3,%4,%5,%6,%7,%8,%9,%10,%11,%12,%13,%14,%15,%16,%17,%18,%19}, %20, %21, p, 1, 1, %23, 1;\n}\n"
               : "+f"(d[0]), "+f"(d[1]), "+f"(d[2]), "+f"(d[3]), "+f"(d[4]), "+f"(d[5]), "+f"(d[6]), "+f"(d[7]), "+f"(d[8]), "+f"(d[9]), "+f"(d[10]), "+f"(d[11]), "+f"(d[12]), "+f"(d[13]), "+f"(d[14]), "+f"(d[15]), "+f"(d[16]), "+f"(d[17]), "+f"(d[18]), "+f"(d[19])
               : "l"(descA), "l"(descB), "n"(scale_d), "n"(tnsp_a));
}
template <int scale_d> __device__ __forceinline__ void wgmma_n40_rs(float* d, const uint32_t* a, uint64_t descB) {
  asm volatile("{\n.reg .pred p;\nsetp.ne.b32 p, %25, 0;\n"
               "wgmma.mma_async.sync.aligned.m64n40k16.f32.bf16.bf16 {%0,%1,%2,%3,%4,%5,%6,%7,%8,%9,%10,%11,%12,%13,%14,%15,%16,%17,%18,%19}, {%20,%21,%22,%23}, %24, p, 1, 1, 1;\n}\n"
               : "+f"(d[0]), "+f"(d[1]), "+f"(d[2]), "+f"(d[3]), "+f"(d[4]), "+f"(d[5]), "+f"(d[6]), "+f"(d[7]), "+f"(d[8]), "+f"(d[9]), "+f"(d[10]), "+f"(d[11]), "+f"(d[12]), "+f"(d[13]), "+f"(d[14]), "+f"(d[15]), "+f"(d[16]), "+f"(d[17]), "+f"(d[18]), "+f"(d[19])
               : "r"(a[0]), "r"(a[1]), "r"(a[2]), "r"(a[3]), "l"(descB), "n"(scale_d));
}
__device__ __forceinline__ void wgmma_copy(float* d, uint32_t da, uint64_t descB) {
  asm volatile("{\n.reg .pred p;\n.reg .b64 a;\nsetp.ne.b32 p, 0, 0;\nmov.b64 a, {%64, 0x40000040};\n"
               "wgmma.mma_async.sync.aligned.m64n16k16.f32.bf16.bf16 {%0,%1,%2,%3,%4,%5,%6,%7}, a, %65, p, 1, 1, 0, 0;\nadd.s64 a, a, 2;\n"
               "wgmma.mma_async.sync.aligned.m64n16k16.f32.bf16.bf16 {%8,%9,%10,%11,%12,%13,%14,%15}, a, %65, p, 1, 1, 0, 0;\nadd.s64 a, a, 2;\n"
               "wgmma.mma_async.sync.aligned.m64n16k16.f32.bf16.bf16 {%16,%17,%18,%19,%20,%21,%22,%23}, a, %65, p, 1, 1, 0, 0;\nadd.s64 a, a, 2;\n"
               "wgmma.mma_async.sync.aligned.m64n16k16.f32.bf16.bf16 {%24,%25,%26,%27,%28,%29,%30,%31}, a, %65, p, 1, 1, 0, 0;\nadd.s64 a, a, 1018;\n"
               "wgmma.mma_async.sync.aligned.m64n16k16.f32.bf16.bf16 {%32,%33,%34,%35,%36,%37,%38,%39}, a, %65, p, 1, 1, 0, 0;\nadd.s64 a, a, 2;\n"
               "wgmma.mma_async.sync.aligned.m64n16k16.f32.bf16.bf16 {%40,%41,%42,%43,%44,%45,%46,%47}, a, %65, p, 1, 1, 0, 0;\nadd.s64 a, a, 2;\n"
               "wgmma.mma_async.sync.aligned.m64n16k16.f32.bf16.bf16 {%48,%49,%50,%51,%52,%53,%54,%55}, a, %65, p, 1, 1, 0, 0;\nadd.s64 a, a, 2;\n"
               "wgmma.mma_async.sync.aligned.m64n16k16.f32.bf16.bf16 {%56,%57,%58,%59,%60,%61,%62,%63}, a, %65, p, 1, 1, 0, 0;\n"
               "}\n"
               : "+f"(d[0]), "+f"(d[1]), "+f"(d[2]), "+f"(d[3]), "+f"(d[4]), "+f"(d[5]), "+f"(d[6]), "+f"(d[7]), "+f"(d[8]), "+f"(d[9]), "+f"(d[10]), "+f"(d[11]), "+f"(d[12]), "+f"(d[13]), "+f"(d[14]), "+f"(d[15]), "+f"(d[16]), "+f"(d[17]), "+f"(d[18]), "+f"(d[19]), "+f"(d[20]), "+f"(d[21]), "+f"(d[22]), "+f"(d[23]), "+f"(d[24]), "+f"(d[25]), "+f"(d[26]), "+f"(d[27]), "+f"(d[28]), "+f"(d[29]), "+f"(d[30]), "+f"(d[31]), "+f"(d[32]), "+f"(d[33]), "+f"(d[34]), "+f"(d[35]), "+f"(d[36]), "+f"(d[37]), "+f"(d[38]), "+f"(d[39]), "+f"(d[40]), "+f"(d[41]), "+f"(d[42]), "+f"(d[43]), "+f"(d[44]), "+f"(d[45]), "+f"(d[46]), "+f"(d[47]), "+f"(d[48]), "+f"(d[49]), "+f"(d[50]), "+f"(d[51]), "+f"(d[52]), "+f"(d[53]), "+f"(d[54]), "+f"(d[55]), "+f"(d[56]), "+f"(d[57]), "+f"(d[58]), "+f"(d[59]), "+f"(d[60]), "+f"(d[61]), "+f"(d[62]), "+f"(d[63])
               : "r"(da), "l"(descB));
}
__device__ __forceinline__ uint64_t make_desc(uint32_t addr, uint32_t lbo_bytes, uint32_t sbo_bytes) {
  return (uint64_t)((addr & 0x3FFFF) >> 4) | ((uint64_t)(lbo_bytes >> 4) << 16) | ((uint64_t)(sbo_bytes >> 4) << 32) | (1ull << 62);
}

__device__ __forceinline__ void ldsm_x4(uint32_t addr, uint32_t& r0, uint32_t& r1, uint32_t& r2, uint32_t& r3) {
  asm volatile("ldmatrix.sync.aligned.m8n8.x4.shared.b16 {%0,%1,%2,%3}, [%4];" : "=r"(r0), "=r"(r1), "=r"(r2), "=r"(r3) : "r"(addr) : "memory");
}
__device__ __forceinline__ void ldsm_x4_t(uint32_t addr, uint32_t& r0, uint32_t& r1, uint32_t& r2, uint32_t& r3) {
  asm volatile("ldmatrix.sync.aligned.m8n8.x4.trans.shared.b16 {%0,%1,%2,%3}, [%4];" : "=r"(r0), "=r"(r1), "=r"(r2), "=r"(r3) : "r"(addr) : "memory");
}
__device__ __forceinline__ void stsm_x4(uint32_t addr, uint32_t r0, uint32_t r1, uint32_t r2, uint32_t r3) {
  asm volatile("stmatrix.sync.aligned.m8n8.x4.shared.b16 [%0], {%1,%2,%3,%4};" :: "r"(addr), "r"(r0), "r"(r1), "r"(r2), "r"(r3) : "memory");
}
__device__ __forceinline__ void stsm_x4_t(uint32_t addr, uint32_t r0, uint32_t r1, uint32_t r2, uint32_t r3) {
  asm volatile("stmatrix.sync.aligned.m8n8.x4.trans.shared.b16 [%0], {%1,%2,%3,%4};" :: "r"(addr), "r"(r0), "r"(r1), "r"(r2), "r"(r3) : "memory");
}
__device__ __forceinline__ void sts128(uint32_t addr, uint32_t a, uint32_t b, uint32_t c, uint32_t d) {
  asm volatile("st.shared.v4.u32 [%0], {%1,%2,%3,%4};" :: "r"(addr), "r"(a), "r"(b), "r"(c), "r"(d) : "memory");
}
__device__ __forceinline__ float lds32f(uint32_t addr) {
  float v;
  asm volatile("ld.shared.f32 %0, [%1];" : "=f"(v) : "r"(addr) : "memory");
  return v;
}
__device__ __forceinline__ void sts32f(uint32_t addr, float a) {
  asm volatile("st.shared.f32 [%0], %1;" :: "r"(addr), "f"(a) : "memory");
}
__device__ __forceinline__ void mma_bf16(float (&c)[4], uint32_t a0, uint32_t a1, uint32_t a2, uint32_t a3, uint32_t b0, uint32_t b1) {
  asm volatile("mma.sync.aligned.m16n8k16.row.col.f32.bf16.bf16.f32 {%0,%1,%2,%3}, {%4,%5,%6,%7}, {%8,%9}, {%0,%1,%2,%3};"
               : "+f"(c[0]), "+f"(c[1]), "+f"(c[2]), "+f"(c[3]) : "r"(a0), "r"(a1), "r"(a2), "r"(a3), "r"(b0), "r"(b1));
}
__device__ __forceinline__ void mma_bf16_z(float (&c)[4], uint32_t a0, uint32_t a1, uint32_t a2, uint32_t a3, uint32_t b0, uint32_t b1) {
  asm volatile("mma.sync.aligned.m16n8k16.row.col.f32.bf16.bf16.f32 {%0,%1,%2,%3}, {%4,%5,%6,%7}, {%8,%9}, {%10,%10,%10,%10};"
               : "=f"(c[0]), "=f"(c[1]), "=f"(c[2]), "=f"(c[3]) : "r"(a0), "r"(a1), "r"(a2), "r"(a3), "r"(b0), "r"(b1), "f"(0.f));
}
__device__ __forceinline__ uint32_t movm_t(uint32_t v) {
  uint32_t r;
  asm volatile("movmatrix.sync.aligned.m8n8.trans.b16 %0, %1;" : "=r"(r) : "r"(v));
  return r;
}
__device__ __forceinline__ uint32_t pack_bf16(float lo, float hi) {
  uint32_t r;
  asm("cvt.rn.bf16x2.f32 %0, %1, %2;" : "=r"(r) : "f"(hi), "f"(lo));
  return r;
}
__device__ __forceinline__ float bf_lo(uint32_t v) { return __uint_as_float(v << 16); }
__device__ __forceinline__ float bf_hi(uint32_t v) { return __uint_as_float(v & 0xFFFF0000u); }
__device__ __forceinline__ void split3(float x, uint32_t& h, uint32_t& m, uint32_t& l) {
  h = pack_bf16(x, 0.f); x -= bf_lo(h);
  m = pack_bf16(x, 0.f); x -= bf_lo(m);
  l = pack_bf16(x, 0.f);
}
__device__ __forceinline__ float ex2(float x) { float r; asm("ex2.approx.ftz.f32 %0, %1;" : "=f"(r) : "f"(x)); return r; }
__device__ __forceinline__ float rcp_fast(float x) { float r; asm("rcp.approx.ftz.f32 %0, %1;" : "=f"(r) : "f"(x)); return r; }
__device__ __forceinline__ void red_v4(float* p, float a, float b, float c, float d) {
  asm volatile("red.global.add.v4.f32 [%0], {%1, %2, %3, %4};" :: "l"(p), "f"(a), "f"(b), "f"(c), "f"(d) : "memory");
}
__device__ __forceinline__ uint4 ld_ll(const uint4* p) {
  uint4 v;
  asm volatile("{\n.reg .b64 a, b;\nld.relaxed.gpu.global.v2.b64 {a, b}, [%4];\nmov.b64 {%0, %1}, a;\nmov.b64 {%2, %3}, b;\n}\n"
               : "=r"(v.x), "=r"(v.y), "=r"(v.z), "=r"(v.w) : "l"(p) : "memory");
  return v;
}
__device__ __forceinline__ void st_b64(uint2* p, uint32_t a, uint32_t b) {
  asm volatile("{\n.reg .b64 v;\nmov.b64 v, {%1, %2};\nst.relaxed.gpu.global.b64 [%0], v;\n}\n" :: "l"(p), "r"(a), "r"(b) : "memory");
}
__device__ __forceinline__ void st_b128(uint4* p, uint32_t a, uint32_t b, uint32_t c, uint32_t d) {
  asm volatile("{\n.reg .b128 v;\nmov.b128 v, {%1, %2, %3, %4};\nst.relaxed.gpu.global.b128 [%0], v;\n}\n" :: "l"(p), "r"(a), "r"(b), "r"(c), "r"(d) : "memory");
}
__device__ __forceinline__ uint4 ld_b128(const uint4* p) {
  uint4 v;
  asm volatile("{\n.reg .b128 v;\nld.relaxed.gpu.global.b128 v, [%4];\nmov.b128 {%0, %1, %2, %3}, v;\n}\n" : "=r"(v.x), "=r"(v.y), "=r"(v.z), "=r"(v.w) : "l"(p) : "memory");
  return v;
}

constexpr float LOG2E = 1.4426950408889634f;

struct Params {
  const __nv_bfloat16* x0;
  const __nv_bfloat16* wA_qkv;
  const __nv_bfloat16* wA_o;
  const __nv_bfloat16* wB_qkv;
  const __nv_bfloat16* wB_phi;
  const __nv_bfloat16* wB_o;
  __nv_bfloat16* out;
};

#define ACC_DEF(d, n) _Pragma("unroll") for (int i_ = 0; i_ < (n); i_++) asm volatile("" : "=f"(d[i_]))
#define ACC_FENCE(d, n) _Pragma("unroll") for (int i_ = 0; i_ < (n); i_++) asm volatile("" : "+f"(d[i_]) :: "memory")
#define PIN(a, n) _Pragma("unroll") for (int i_ = 0; i_ < (n); i_++) asm volatile("" : "+f"((a)[i_]))
#define PINU(a, n) _Pragma("unroll") for (int i_ = 0; i_ < (n); i_++) asm volatile("" : "+r"((a)[i_]))

#define V_ADDR(p0, sw) uint32_t va_[2] = {(p0) + (srowoff >> 1) + (lhi ^ lsw2 ^ (sw)), (p0) + (srowoff >> 1) + ((32 + lhi) ^ lsw2 ^ (sw))}
#define STAGE_V(acc) { \
    _Pragma("unroll") for (int j_ = 0; j_ < 4; j_++) { \
      const float* a_ = (acc) + j_ * 8; \
      stsm_x4(va_[j_ & 1] + (j_ >> 1) * 8192, \
              pack_bf16(rs0 * a_[0], rs0 * a_[1]), pack_bf16(rs1 * a_[2], rs1 * a_[3]), pack_bf16(rs0 * a_[4], rs0 * a_[5]), pack_bf16(rs1 * a_[6], rs1 * a_[7])); } }
#define FRAG(dst, acc, TR, grp) { \
    _Pragma("unroll") for (int i_ = 15; i_ >= 0; i_--) { \
      const float r_ = (i_ & 8) ? rs1 : rs0; \
      const uint32_t w_ = pack_bf16(r_ * (acc)[4 * (i_ & 7) + (i_ >> 3) * 2], r_ * (acc)[4 * (i_ & 7) + (i_ >> 3) * 2 + 1]); \
      (dst)[8 + i_] = (TR) ? movm_t(w_) : w_; \
      if (i_ == 8 && warp >= 6 && mm < 15) { \
        _Pragma("unroll") for (int j_ = 0; j_ < 2; j_++) \
          st_b128(g_halo + (size_t)(mm * 8 + jj) * 512 + ((grp) * 4 + warp * 2 - 12 + j_) * 32 + lane, ((dst)[16 + j_ * 4] & ~1u) | H_BIT(l), (dst)[17 + j_ * 4], (dst)[18 + j_ * 4], (dst)[19 + j_ * 4]); } } \
    PINU((dst) + 8, 16); }
#define FRAG_PUT(src, slot) if (warp < 6) { _Pragma("unroll") for (int j_ = 0; j_ < 2; j_++) \
      sts128(sbase + OFF_S + (slot) * 8192 + 2048 + warp * 1024 + j_ * 512 + lane * 16, (src)[j_ * 4], (src)[j_ * 4 + 1], (src)[j_ * 4 + 2], (src)[j_ * 4 + 3]); }
#define FRAG_GET(dst, slot) { _Pragma("unroll") for (int j_ = 0; j_ < 2; j_++) \
      asm volatile("ld.shared.v4.u32 {%0, %1, %2, %3}, [%4];" : "=r"((dst)[j_ * 4]), "=r"((dst)[j_ * 4 + 1]), "=r"((dst)[j_ * 4 + 2]), "=r"((dst)[j_ * 4 + 3]) \
                   : "r"(sbase + OFF_S + (slot) * 8192 + warp * 1024 + j_ * 512 + lane * 16) : "memory"); }
#define RW(j) (((j) >> 1) * 4 + ((j) & 1))
template <int POS> __device__ __forceinline__ float exps16_(float* o, const float* p) {
  float s[4];
#pragma unroll
  for (int j = 0; j < 16; j++) { o[j] = ex2(POS ? p[RW(j)] : -p[RW(j)]); if (j < 4) s[j] = o[j]; else s[j & 3] += o[j]; }
  const float r = (s[0] + s[1]) + (s[2] + s[3]);
  return r + __shfl_xor_sync(0xffffffffu, r, 1);
}
template <int POS> __device__ __forceinline__ void exps16_fix(float* o, const float* p, float& sum) {
  if (__builtin_expect(__any_sync(0xffffffffu, !(sum > SUMLO && sum < SUMHI)), 0)) {
    float m = p[0], q[32];
#pragma unroll
    for (int j = 1; j < 16; j++) m = POS ? fmaxf(m, p[RW(j)]) : fminf(m, p[RW(j)]);
    const float x = __shfl_xor_sync(0xffffffffu, m, 1);
    m = POS ? fmaxf(m, x) : fminf(m, x);
#pragma unroll
    for (int j = 0; j < 16; j++) q[RW(j)] = p[RW(j)] - m;
    sum = exps16_<POS>(o, q);
  }
}
__device__ __forceinline__ void store16(const float* e, float sum, uint32_t dst, uint32_t dsw, int c0) {
  const float inv = rcp_fast(sum);
#pragma unroll
  for (int j = 0; j < 2; j++)
    sts128(dst + (((c0 + j) << 4) ^ dsw), pack_bf16(e[j * 8] * inv, e[j * 8 + 1] * inv), pack_bf16(e[j * 8 + 2] * inv, e[j * 8 + 3] * inv),
           pack_bf16(e[j * 8 + 4] * inv, e[j * 8 + 5] * inv), pack_bf16(e[j * 8 + 6] * inv, e[j * 8 + 7] * inv));
}
template <int POS> __device__ __forceinline__ void expp16(uint32_t* o, float* p) {
  {
#pragma unroll
    for (int r = 0; r < 4; r += 2) {
      float m = p[r];
#pragma unroll
      for (int j = 1; j < 8; j++) m = POS ? fmaxf(m, p[r + RW(j)]) : fminf(m, p[r + RW(j)]);
#pragma unroll
      for (int s = 1; s <= 2; s <<= 1) { const float x = __shfl_xor_sync(0xffffffffu, m, s); m = POS ? fmaxf(m, x) : fminf(m, x); }
#pragma unroll
      for (int j = 0; j < 8; j++) p[r + RW(j)] -= m;
    }
  }
#pragma unroll
  for (int j = 0; j < 8; j++) o[j] = pack_bf16(ex2(POS ? p[2 * j] : -p[2 * j]), ex2(POS ? p[2 * j + 1] : -p[2 * j + 1]));
}
__device__ __forceinline__ void scale32(float* o, const float* p, float c0, float c1) {
#pragma unroll
  for (int i = 0; i < 32; i++) asm volatile("mul.f32 %0, %1, %2;" : "=f"(o[i]) : "f"(p[i]), "f"((i & 2) ? c1 : c0));
}
__device__ __forceinline__ bool any_big(const float* p) {
  float m[4];
#pragma unroll
  for (int i = 0; i < 32; i++) m[i >> 3] = (i & 7) ? fmaf(p[i], p[i], m[i >> 3]) : p[i] * p[i];
  return __any_sync(0xffffffffu, !(fmaxf(fmaxf(m[0], m[1]), fmaxf(m[2], m[3])) < BIGLIM));
}
__device__ __forceinline__ void phiq_a(float* p, bool big) {
  if (__builtin_expect(!big, 1)) {
#pragma unroll
    for (int j = 0; j < 16; j++) p[j] = ex2(p[j]);
  }
}
template <int NEXT> __device__ __forceinline__ void phiq_b(uint32_t* o, float* p, bool big) {
  if (__builtin_expect(big, 0)) {
    expp16<0>(o, p); expp16<1>(o + 8, p);
  } else {
    if (NEXT) phiq_a(p + 16, false);
#pragma unroll
    for (int j = 0; j < 4; j++) {
      const float a = p[4 * j], b = p[4 * j + 1], c = p[4 * j + 2], d = p[4 * j + 3];
      const float ab = a * b, cd = c * d, r = rcp_fast(ab * cd), x = r * cd, y = r * ab;
      o[2 * j] = pack_bf16(x * b, x * a); o[2 * j + 1] = pack_bf16(y * d, y * c);
      o[8 + 2 * j] = pack_bf16(a, b); o[9 + 2 * j] = pack_bf16(c, d);
    }
  }
}
#define SCHED_FENCE() asm volatile("pmevent 0;" ::: "memory")

__global__ void __cluster_dims__(2, 1, 1) __launch_bounds__(384, 1)
mega_kernel(const __grid_constant__ CUtensorMap tm_x0, const __grid_constant__ CUtensorMap tm_xo, const __grid_constant__ CUtensorMap tm_os,
            const __grid_constant__ CUtensorMap tm_o, const __grid_constant__ CUtensorMap tm_wf,
            const __grid_constant__ CUtensorMap tm_wqA, const __grid_constant__ CUtensorMap tm_wqB,
            const __grid_constant__ CUtensorMap tm_woA, const __grid_constant__ CUtensorMap tm_woB,
            const __grid_constant__ CUtensorMap tm_phi, const Params prm) {
  extern __shared__ __align__(1024) uint8_t smem_raw[];
  const uint32_t sbase = smem_u32(smem_raw);
  const uint32_t bar_full = sbase + OFF_BAR;
  const uint32_t bar_done = bar_full + 384;
  const uint32_t bar_stat = bar_full + 768, bar_stat2 = bar_full + 776, bar_epi = bar_full + 784, bar_phi = bar_full + 936  , bar_halo = bar_full + 904  ;
  const uint32_t bar_xr = bar_full + 800, bar_lx = bar_full + 808, bar_stg = bar_full + 832;
  const uint32_t bar_chk = bar_full + 848;

  const int warp = __shfl_sync(0xffffffffu, threadIdx.x >> 5, 0), lane = threadIdx.x & 31;
  const uint32_t bar_kx = sbase + OFF_ID + 384 + warp * 8;
  uint32_t rank;
  asm volatile("mov.u32 %0, %%cluster_ctarank;" : "=r"(rank));
  const int aux = (int)blockIdx.x - NMAIN, tp = (int)(blockIdx.x >> 1) - 4;
  const int gp = tp < 0 ? 0 : (tp < 32 ? tp & 7 : 1 + (tp - 32) % 7), me = tp < 0 ? tp + 8 : (tp < 32 ? tp >> 3 : 4 + (tp - 32) / 7);
  const int jj = me, cc = gp;
  const int cta = aux >= 0 ? -1 : (cc * 8 + jj) * 2 + (int)rank;
  const int mm = cc * 2 + (int)rank;

#define LOAD_EPOCH() const unsigned epoch = ld_relaxed(&g_flags.epoch.v), ep1 = epoch + 1; (void)epoch
  int budget = 1 << 22;

  if (cta >= 0) {
    if (warp >= 8 && warp < 8 + EARLY && elect_one()) {
      const int u = warp - 8;
      const uint32_t fb = bar_full + u * 8;
      mbar_init(fb, 1);
      asm volatile("fence.mbarrier_init.release.cluster;" ::: "memory");
      fence_proxy_async_smem();
      mbar_expect_tx(fb, QST + SLOT);
      if (u) __nanosleep(STAG2);
      tma_load_t(sbase + OFF_S + u * SLOT, &tm_x0, fb, jj * 128 + u * 64, mm * 128);
#pragma unroll
      for (int i = 0; i < 6; i++) tma_load_2d(sbase + u * QST + i * 4096, &tm_wqA, fb, jj * 128 + (i >> 1) * 1024, jj * 128 + u * 64 + (i & 1) * 32);
      if (u == 0) PROFT(472);
    }
    __syncwarp();
    {
      const int tx = threadIdx.x;
      const __nv_bfloat16* pf = (tx < 128) ? prm.x0 + (size_t)(mm * 128 + tx) * D_MODEL + jj * 128
                                           : prm.wA_qkv + (size_t)(jj * 128 + (tx & 63)) * 3072 + ((tx - 128) >> 6) * 1024 + jj * 128 + rank * 64;
      if (tx < 320) asm volatile("prefetch.global.L2 [%0];" :: "l"(pf));
      else if (tx == 320) prefetch_tmap(&tm_x0);
      else if (tx == 352) prefetch_tmap(&tm_wqA);
      else if (tx == 383) asm volatile("prefetch.global.L2 [%0];" :: "l"(&g_flags.epoch.v));
    }
    if (elect_one()) {
#pragma unroll
      for (int i = 0; i < 4; i++) {
        const int u = warp * 4 + i;
        if (u >= EARLY) mbar_init(bar_full + u * 8, ((u >= 4 && u < 11) || (u > 32 && u != 40)) ? 2 : 1); mbar_init(bar_done + u * 8, 16);
      }
      mbar_init(bar_stat + warp * 16, 0x111111181182ull >> (4 * warp) & 15);
      mbar_init(bar_stat + warp * 16 + 8, 0x111111121811ull >> (4 * warp) & 15);
      mbar_init(bar_chk + 112 + (warp & 7) * 8, 1);
      mbar_init(bar_kx, 1);
      asm volatile("fence.mbarrier_init.release.cluster;" ::: "memory");
    }
    __syncwarp();
    __syncthreads();
    asm volatile("barrier.cluster.arrive.relaxed.aligned;" ::: "memory");
  }

  if (cta < 0) {
    LOAD_EPOCH();
    const uint32_t buf = sbase + warp * SLOT, bar = sbase + OFF_BAR + warp * 16;
    const uint32_t lsw = (lane & 7) << 4, lhi = (lane >> 4) << 4, lrow = (lane & 15) * 128;
    const bool el = elect_one();
    if (el) {
      mbar_init(bar, 1); mbar_init(bar + 8, 1);
      asm volatile("fence.mbarrier_init.release.cluster;" ::: "memory");
    }
#pragma unroll 1
    for (int rd = 0; rd < (NLAYERS > 1 ? 5 : 2); rd++) {
      if (rd >= 2 && warp >= 8) break;
      const int tk = rd < 2 ? aux * 12 + warp : aux * 8 + warp;
      const int half = tk & 1;
      const int blk = rd < 2 ? (tk >> 1) * 2 + rd : (4 - rd) * 16 + (tk >> 1);
      const CUtensorMap* tm = rd < 2 ? &tm_wqA : (rd == 2 ? &tm_wqB : &tm_wf);
      const int j0 = (blk & 15) >> 1;
#define AUX_LOAD(n) { const uint32_t d_ = buf + ((n) & 1) * 8192, b_ = bar + ((n) & 1) * 8; const int r_ = kslice(j0, 2 * (n) + half) * 64; \
        mbar_expect_tx(b_, 8192); tma_load_2d(d_, tm, b_, blk * 64, r_); tma_load_2d(d_ + 4096, tm, b_, blk * 64, r_ + 32); }
      if (el) {
        if (rd == 3) { wait_flag(&g_flags.wfready[j0].v, ep1 * 16); fence_proxy_async_global(); }
        AUX_LOAD(0); AUX_LOAD(1);
      }
      __syncwarp();
      float cs[8][4];
#pragma unroll
      for (int i = 0; i < 8; i++) cs[i][0] = cs[i][1] = cs[i][2] = cs[i][3] = 0.f;
#pragma unroll 1
      for (int n = 0; n < 8; n++) {
        const uint32_t tb = buf + (n & 1) * 8192 + lrow;
        mbar_wait(bar + (n & 1) * 8, (n >> 1) & 1);
#pragma unroll
        for (int i = 0; i < 16; i++) {
          uint32_t b0, b1, b2, b3;
          ldsm_x4_t(tb + (i >> 2) * 2048 + (((i & 3) * 32 + lhi) ^ lsw), b0, b1, b2, b3);
          mma_bf16(cs[2 * (i & 3)], 0x3F803F80u, 0x3F803F80u, 0x3F803F80u, 0x3F803F80u, b0, b1);
          mma_bf16(cs[2 * (i & 3) + 1], 0x3F803F80u, 0x3F803F80u, 0x3F803F80u, 0x3F803F80u, b2, b3);
        }
        __syncwarp();
        if (el && n < 6) AUX_LOAD(n + 2);
        __syncwarp();
      }
      if (lane < 4) {
#pragma unroll
        for (int i = 0; i < 8; i++) st_b64(&g_colsum[rd >= 2][blk * 32 + i * 4 + lane][half], __float_as_uint(cs[i][0]), (__float_as_uint(cs[i][1]) & ~3u) | (ep1 & 3));
      }
      __syncwarp();
    }
  } else if (warp >= 8) {
    asm volatile("setmaxnreg.dec.sync.aligned.u32 40;");
    if (warp == 8) {
      const bool el = elect_one();
      cluster_wait();
      if (el) {
#pragma unroll 1
        for (int l = 0; l < NLAYERS; l++) {
          const uint32_t par = l & 1;
          const CUtensorMap* tqk = par ? &tm_wf : &tm_wqA;
          const CUtensorMap* tv = par ? &tm_wqB : &tm_wqA;
          const CUtensorMap* two = par ? &tm_woB : &tm_woA;
          if (l == 1) { LOAD_EPOCH(); wait_flag(&g_flags.wfready[jj].v, ep1 * 16); fence_proxy_async_global(); }
#pragma unroll 1
          for (int u = l ? 0 : EARLY; u < 32; u++) {
            if (u >= 4) mbar_wait_sl(bar_done + (u - 4) * 8, par);
            else if (l) mbar_wait_sl(bar_done + (43 + u + (u >> 1)) * 8, par ^ 1);
            else mbar_wait_sl(bar_full, 0);
            const uint32_t fb = bar_full + u * 8;
            const bool res = u < 11 || (u >= 18 && u < 22);
            mbar_expect_tx(fb, res ? QST : QST + SLOT);
            const int row = kslice(jj, u < 4 ? u & 1 : (u < 18 ? u - 2 : (u < 22 ? u - 6 : u - 20))) * 64 + (int)rank * 32;
            const int ps = u < 4 ? u >> 1 : (u >= 18), col = jj * 128 + ps * 64;
            const int c0 = par ? jj * 128 + (ps ? 0 : 1024) : col;
            const uint32_t dst = sbase + (u & 3) * QST + rank * 4096;
            tma_load_2d_mc(dst, tqk, fb, c0, row);
            tma_load_2d_mc(dst + 8192, tqk, fb, c0 + (par ? 64 : 1024), row);
            tma_load_2d_mc(dst + 16384, tv, fb, col + 2048, row);
            if (l == PRL && u >= PRU && u < PRU + 4) PROFT(473 + u - PRU);
          }
#pragma unroll 1
          for (int s = 0; s < 16; s++) {
            if (s < 5) { if (s != 2 && s != 4) mbar_wait_sl(bar_done + (28 + s) * 8, par); }
            else if (s != 14) mbar_wait_sl(bar_done + (27 + s - (s == 15)) * 8, par);
            const uint32_t fb = bar_full + (32 + s) * 8;
            mbar_expect_tx(fb, SLOT);
            tma_load_2d_mc(sbase + rank * 8192 + (uint32_t)((WO_BSLOT >> (4 * s)) & 15) * SLOT, two, fb, jj * 128 + (int)rank * 64, wslice(jj, s) * 64);
            const int ts = s + 1;
            if (s >= 5 && ts < 8) {
              mbar_expect_tx(bar_chk - 8 + ts * 8, SLOT);
              tma_load_t(sbase + (uint32_t)((WO_ASLOT(par) >> (4 * ts)) & 15) * SLOT, &tm_o, bar_chk - 8 + ts * 8, wslice(jj, ts) * 64, mm * 128);
            }
          }
        }
      }
      __syncwarp();
    } else if (warp == 9) {
      const bool el = elect_one();
      LOAD_EPOCH();
#pragma unroll 1
      for (int lp = 0; lp < 4 * NLAYERS; lp++) {
        const int l = lp >> 2, ph = lp & 3;
        if (ph == 3) continue;
        const uint32_t par = l & 1;
        const unsigned* pp = reinterpret_cast<const unsigned*>(g_obuf + (ph >> 1) * 64 + (size_t)(mm * 128 + (ph ? 0 : S_LEN) + ((lane & 7) | PROWS) * 16 + (jj & 1) * 8) * D_MODEL +
                                                               (jj >> 1) * 16 + srcb(jj, lane >> 3) * 128);
        const CUtensorMap* tm = lp ? &tm_o : &tm_x0;
        const int row = mm * 128 + ((ph || !l) ? 0 : S_LEN);
        const uint32_t bit = ph ? O_BIT(l) : X_BIT(l - 1);
        const uint32_t slots = ph ? (uint32_t)(WO_ASLOT(par) >> (ph * 32 - 28)) : 0x8769876u;
        const unsigned long long fr = ph == 0 ? XPACE : ph == 1 ? (par ? FRB : 0x35351F1E1Dull) : 0x27262524232232ull;
        uint32_t no = (lp == 0 || (lp & 7) == 1) ? 0 : (ph == 1 ? NOB : (ph ? NO1 : NOX)), v0 = 0, v1 = 0;
        mbar_wait_sl(ph ? bar_done + ((uint32_t)fr & 63) * 8 : (l ? bar_done + 47 * 8 : bar_full), ph ? par : (l ? par ^ 1 : 0));
        if (el && ph) PROFT(324 + l * 16 + ph);
        __syncwarp();
        if (no && (ph == 1 ? SPD1 : (ph ? SPD2 : SPD0))) __nanosleep(ph == 1 ? SPD1 : (ph ? SPD2 : SPD0));
        if (no) { v0 = ld_relaxed(pp); __nanosleep(POLLGAP); v1 = ld_relaxed(pp); }
#pragma unroll 1
        for (int i = 0; i < (ph == 1 ? 5 : 7); i++, no >>= 8) {
#pragma unroll 1
          for (int it = 0; (no & 0xFF) && it < (1 << 18); it++) {
            no &= __ballot_sync(0xffffffffu, (v0 ^ bit) & 1) >> (8 * i);
            if (no) v0 = ld_relaxed(pp);
            if (!(no & 0xFF)) break;
            no &= __ballot_sync(0xffffffffu, (v1 ^ bit) & 1) >> (8 * i);
            if (no) v1 = ld_relaxed(pp);
          }
          if (ph || i >= XP0) mbar_wait_sl(bar_done + ((uint32_t)(fr >> (8 * i)) & 63) * 8, par);
          if (el) {
            if (i == 0) PROFT(320 + l * 16 + ph);
            const uint32_t cb = (lp ? bar_chk + (ph >> 1) * 112 : bar_full + 32) + i * 8;
            mbar_expect_tx(cb, SLOT);
            tma_load_t(sbase + ((slots >> (4 * i)) & 15) * SLOT, tm, cb, srcb(jj, i) * 128 + (ph >> 1) * 64, row);
          }
          __syncwarp();
        }
        if (ph == 0 && el) {
          if (l) { wait_flag(&g_flags.xready[l][mm].v, ep1 * 8); fence_proxy_async_global(); }
#pragma unroll 1
          for (int u = 11; u < 34; u++) {
            if (u == 18) u = 22;
            mbar_wait_sl(bar_done + (u - 4) * 8, par);
            if (u == 32) mbar_expect_tx(bar_xr, 2 * SLOT);
            tma_load_t(sbase + OFF_RA + (u & 3) * SLOT, tm, u < 32 ? bar_full + u * 8 : bar_xr, kslice(jj, u < 18 ? u - 2 : (u < 32 ? u - 20 : u - 32)) * 64, row);
          }
        }
        __syncwarp();
      }
      if (el && atomicAdd(&g_flags.done.v, 1) == ep1 * NMAIN - 1) asm volatile("st.relaxed.gpu.global.u32 [%0], %1;" :: "l"(&g_flags.epoch.v), "r"(ep1) : "memory");
      __syncwarp();
      cluster_wait();
    } else {
      const int hw = warp - 10;
      LOAD_EPOCH();
      const bool el = elect_one();
      cluster_wait();
      if (hw == 0) {
        mbar_wait_sl(bar_full + 8, 0);
        if (lane < 7) prefetch_tmap(lane == 0 ? &tm_os : lane == 1 ? &tm_o : lane == 2 ? &tm_wf : lane == 3 ? &tm_wqB : lane == 4 ? &tm_woA : lane == 5 ? &tm_woB : &tm_phi);
#pragma unroll 1
        for (int i = 0; i < (NLAYERS > 1 ? 9 : 0); i++) {
          if (i == 0 || i == 5) mbar_wait_sl(bar_done + (i ? FD1 : FD0) * 8, 0);
          if (el) {
            if (i == 0) { mbar_expect_tx(bar_phi, 2 * SLOT + 8192); tma_load_2d(sbase + OFF_PHI, &tm_phi, bar_phi, 0, jj * 128); }
            else tma_load_2d(sbase + (i > 4 ? 10 : 12) * SLOT - 4096 + i * 4096, &tm_wqB, bar_phi, (i > 4 ? 896 : 0) + jj * 128 + ((i - 1) >> 1) * 64, mm * 64 + (~i & 1) * 32);
          }
          __syncwarp();
          __nanosleep(PFGAP);
        }
      } else {
        if (lane < 24) {
          const uint32_t one = (lane & 8) ? 0u : 0x3F80u << ((lane & 1) * 16), w = (lane >> 1) & 3;
          sts128(sbase + OFF_ID + lane * 16, w == 0 ? one : 0u, w == 1 ? one : 0u, w == 2 ? one : 0u, w == 3 ? one : 0u);
        }
#pragma unroll 1
        for (int b = 0; b < 2; b++) {
          float4* z = reinterpret_cast<float4*>(g_kv[b] + (jj * 4) * KVH + mm * (4 * KVH / 16)) + lane;
#pragma unroll
          for (int i = 0; i < 6; i++) z[i * 32] = make_float4(0.f, 0.f, 0.f, 0.f);
        }
#pragma unroll 1
        for (int i = 0; i < 16; i++) {
          const int b = i >> 2;
          const uint32_t v = (b == 0 ? O_BIT(0) : b == 1 ? X_BIT(0) : H_BIT(0)) + 1;
          uint4* p = b < 2 ? reinterpret_cast<uint4*>(g_obuf + (size_t)(b * S_LEN + mm * 128 + (i & 3) * 32 + (lane >> 3) * 8) * D_MODEL + jj * 128 + (b ? 0 : 64)) + (lane & 7)
                           : g_halo + (size_t)(mm * 8 + jj) * 512 + i * 32 + lane;
          *p = make_uint4(v, v, v, v);
        }
        fence_proxy_async_global();
      }
      __syncwarp();
      uint32_t chkp = 0;
#pragma unroll 1
      for (int lp = hw; lp < 8 * NLAYERS; lp++) {
        const int l = lp >> 3, tk = lp & 7, ph = tk ? 2 - hw : 0;
        const uint32_t par = l & 1;
        int lane; asm volatile("mov.u32 %0, %%laneid;" : "=r"(lane));
        if (tk == 5 || (hw && tk == 0)) {
          const uint32_t bit = ph ? O_BIT(l) : X_BIT(l - 1);
          uint32_t slots = ph ? (uint32_t)(WO_ASLOT(par) >> (ph * 32 - 28)) : 0x8769876u;
          const uint32_t a0 = sbase + (lane & 7) * 126 + lane * 4 + (lane & 1) * 14;
#pragma unroll 1
          for (int c = 0; c < 7; c++, slots >>= 4) {
            const uint32_t cb = bar_chk + 112 - hw * 112 + c * 8;
#pragma unroll 1
            for (int it = 0; it < (1 << 12); it++) {
              mbar_wait_sl(cb, (chkp >> c) & 1);
              chkp ^= 1u << c;
              if (el && c == 0) PROFT(ph == 1 ? 480 + l * 2 : 488 + l * 2 + (ph >> 1));
              uint32_t bad;
              asm volatile("{\n.reg .b32 w<16>;\n"
                           "ld.shared.u32 w0, [%1 + 0];\n"
                           "ld.shared.u32 w1, [%1 + 1024];\n"
                           "ld.shared.u32 w2, [%1 + 2048];\n"
                           "ld.shared.u32 w3, [%1 + 3072];\n"
                           "ld.shared.u32 w4, [%1 + 4096];\n"
                           "ld.shared.u32 w5, [%1 + 5120];\n"
                           "ld.shared.u32 w6, [%1 + 6144];\n"
                           "ld.shared.u32 w7, [%1 + 7168];\n"
                           "ld.shared.u32 w8, [%1 + 8192];\n"
                           "ld.shared.u32 w9, [%1 + 9216];\n"
                           "ld.shared.u32 w10, [%1 + 10240];\n"
                           "ld.shared.u32 w11, [%1 + 11264];\n"
                           "ld.shared.u32 w12, [%1 + 12288];\n"
                           "ld.shared.u32 w13, [%1 + 13312];\n"
                           "ld.shared.u32 w14, [%1 + 14336];\n"
                           "ld.shared.u32 w15, [%1 + 15360];\n"
                           "lop3.b32 w0, w0, w1, %2, 0x7E;\n"
                           "lop3.b32 w2, w2, w3, %2, 0x7E;\n"
                           "lop3.b32 w4, w4, w5, %2, 0x7E;\n"
                           "lop3.b32 w6, w6, w7, %2, 0x7E;\n"
                           "lop3.b32 w8, w8, w9, %2, 0x7E;\n"
                           "lop3.b32 w10, w10, w11, %2, 0x7E;\n"
                           "lop3.b32 w12, w12, w13, %2, 0x7E;\n"
                           "lop3.b32 w14, w14, w15, %2, 0x7E;\n"
                           "lop3.b32 w0, w0, w2, w4, 0xFE;\nlop3.b32 w6, w6, w8, w10, 0xFE;\nlop3.b32 w0, w0, w12, w14, 0xFE;\nlop3.b32 %0, w0, w6, 1, 0xA8;\n}\n"
                           : "=r"(bad) : "r"(a0 + (slots & 15) * SLOT), "r"(bit) : "memory");
              if (__all_sync(0xffffffffu, bad == 0)) break;
              if (el) {
                fence_proxy_async_smem();
                mbar_expect_tx(cb, SLOT);
                tma_load_t(sbase + (slots & 15) * SLOT, &tm_o, cb, srcb(jj, c) * 128 + (ph >> 1) * 64, mm * 128 + (ph ? 0 : S_LEN));
                RETRY_COUNT();
              }
              __syncwarp();
            }
            if (el) { mbar_arrive_local(bar_full + (c + (ph ? 25 + ph * 8 : 4)) * 8); if (lp == PRL * 8 && c == 0) PROFT(477); }
            __syncwarp();
          }
        } else if (hw && (tk & 5) == 1) {
          {
            const int hp = tk >> 1;
            const uint4* src = reinterpret_cast<const uint4*>(g_colsum[par][jj * 64 + hp * 32 + lane]);
            uint32_t bad;
            int it = 0;
            float c[6];
            do {
              bad = 0;
#pragma unroll
              for (int p = 0; p < 3; p++) {
                const uint4 v = ld_ll(src + ((par && p < 2) ? (hp ? -32 : 512) + p * 32 : p * 512));
                bad |= (v.y ^ ep1) | (v.w ^ ep1);
                c[2 * p] = __uint_as_float(v.x) + __uint_as_float(v.z); c[2 * p + 1] = __uint_as_float(v.y) + __uint_as_float(v.w);
              }
              bad &= 3;
              if (bad) __nanosleep(300);
            } while (bad && ++it < (1 << 16));
#pragma unroll
            for (int p = 0; p < 6; p++) {
              uint32_t h, m, lo;
              split3(c[p], h, m, lo);
              sts128(sbase + OFF_LNB + hp * 4096 + (p >> 1) * 1024 + lane * 32 + (p & 1) * 16, h | (m << 16), h | (lo << 16), h | (m << 16), lo | (m << 16));
            }
            fence_proxy_async_smem();
            __syncwarp();
            if (el) { mbar_arrive_local(hp ? bar_stat2 : bar_stat); if (hp == 0) PROFT(324 + l * 16); }
            __syncwarp();
          }
        } else if (tk == 0) {
          mbar_wait_sl(bar_done + 24, par);
          const uint4* sp = reinterpret_cast<const uint4*>(g_stats + (size_t)(mm * 128) * 8) + lane;
#pragma unroll 1
          for (int hf = 0; hf < 4; hf++) {
            uint4 v[4];
            uint32_t bad;
            int it = 0;
            do {
              bad = 0;
#pragma unroll
              for (int i = 0; i < 4; i++) { v[i] = ld_ll(sp + (hf * 4 + i) * 32); bad |= (v[i].y ^ STAT_TAG(l)) | (v[i].w ^ STAT_TAG(l)); }
              bad &= 3;
              if (bad) __nanosleep(200);
            } while (bad && ++it < (1 << 16));
            __syncwarp();
            float mean = 0.f, m2 = 0.f;
#pragma unroll
            for (int i = 0; i < 4; i++) {
              float a = __uint_as_float(v[i].x) + __uint_as_float(v[i].z);
              a += __shfl_xor_sync(0xffffffffu, a, 1); a += __shfl_xor_sync(0xffffffffu, a, 2);
              a *= 0.125f;
              const float e0 = __uint_as_float(v[i].x) - a, e1 = __uint_as_float(v[i].z) - a;
              float q = fmaf(fmaf(e0, e0, e1 * e1), 128.f, __uint_as_float(v[i].y) + __uint_as_float(v[i].w));
              q += __shfl_xor_sync(0xffffffffu, q, 1); q += __shfl_xor_sync(0xffffffffu, q, 2);
              if ((lane & 3) == i) { mean = a; m2 = q; }
            }
            const uint32_t row = hf * 32 + (lane & 3) * 8 + (lane >> 2);
            uint32_t h, m, lo;
            split3(-0.5f * mean, h, m, lo);
            sts128(sbase + OFF_LNA + row * 16, h | (h << 16), m | (h << 16), lo | (m << 16), m | (lo << 16));
            sts32f(sbase + OFF_ST + row * 4, rsqrtf(m2 * (1.f / 1024.f) + 1e-5f));
          }
          fence_proxy_async_smem();
          __syncwarp();
          if (el) { mbar_arrive_local(bar_stat); PROFT(323 + l * 16); }
          __syncwarp();
#pragma unroll 1
          for (int i = 0; i < 8 - 4 * l; i++) {
            asm volatile("prefetch.global.L2 [%0];" :: "l"(i < 4 ? (l ? prm.wB_o : prm.wA_o) + (size_t)cta * 8192 + i * 2048 + lane * 64
                                                                 : prm.wB_qkv + (size_t)(cta * 8 + (i - 4) * 2 + (lane >> 4)) * 3072 + 2048 + (lane & 15) * 64));
            __nanosleep(PFGAP);
          }
        } else if (lp == 3) {
#pragma unroll 1
          for (int c = 0; c < (NLAYERS > 1 ? 8 : 0); c++) {
            if (!(c & 3)) asm volatile("bar.sync %0, 288;" :: "r"(BAR_WF + (c >> 2)) : "memory");
            if (el) {
              tma_store_2d(&tm_wf, sbase + 11 * SLOT + c * 4096, (c < 4 ? 1024 : -128) + jj * 128 + (c >> 1) * 64, mm * 64 + (c & 1) * 32);
              if (c == 7) {
                asm volatile("cp.async.bulk.commit_group;\ncp.async.bulk.wait_group.read 0;" ::: "memory");
                mbar_arrive_local(bar_phi + 8);
              } else __nanosleep(WFGAP);
            }
            __syncwarp();
          }
          if (el) { bulk_commit_wait(); signal_release(&g_flags.wfready[jj].v); PROFT(335); }
          __syncwarp();
        } else if (tk == 2 || tk == 4) {
          if (par) continue;
          const int i = tk >> 2;
          mbar_wait_sl(bar_done + (i ? HW1 : (hw ? 19 : HW0)) * 8, 0);
          const uint4* src = g_halo + (size_t)(mm * 8 + jj - 8) * 512 + i * 256 + hw * 128 + lane;
          uint4 v[4];
          int it = 0;
          bool ok;
          do {
#pragma unroll
            for (int j = 0; j < 4; j++) v[j] = mm ? ld_b128(src + j * 32) : make_uint4(H_BIT(l), 0, 0, 0);
            ok = __all_sync(0xffffffffu, (((v[0].x ^ H_BIT(l)) | (v[1].x ^ H_BIT(l)) | (v[2].x ^ H_BIT(l)) | (v[3].x ^ H_BIT(l))) & 1) == 0);
          } while (!ok && ++it < (1 << 16));
#pragma unroll
          for (int j = 0; j < 4; j++) sts128(sbase + OFF_S + hw * 8192 + j * 512 + lane * 16, v[j].x, v[j].y, v[j].z, v[j].w);
          __syncwarp();
          if (el) { mbar_arrive_local(bar_halo + hw * 8); PROFT(331 + l * 16 + i * 2 + hw); }
          __syncwarp();
        } else if (tk == 6 && hw == 0 && l < NLAYERS - 1) {
          bar_sync<BAR_X1, 288>();
          if (el) {
            PROFT(328 + l * 16);
            mbar_wait_sl(bar_full + XD * 8, par ^ 1);
            tma_store_t(&tm_o, sbase + 11 * SLOT, jj * 128 + 64, mm * 128 + S_LEN);
            bulk_commit_wait();
            signal_release(&g_flags.xready[l + 1][mm].v);
            PROFT(330 + l * 16);
          }
          __syncwarp();
        }
      }
    }
    cluster_sync();
  } else {
    asm volatile("setmaxnreg.inc.sync.aligned.u32 232;");
    const int wg = warp >> 2;
    const int r0 = warp * 16;
    const uint32_t pK = sbase + OFF_S, pV = sbase + OFF_S + SLOT;
#define PMASKS(on, bit) const uint32_t pm0 = ((on) && t == (g >> 1)), pbit = (bit)
#define PBIT(w) (((w) & ~pm0) | (pbit & pm0))
#define LANE_CONSTS() \
    int lane; asm volatile("mov.u32 %0, %%laneid;" : "=r"(lane)); \
    const int g = lane >> 2, t = lane & 3; \
    const uint32_t srowoff = (r0 + (lane & 15)) * 128, lsw = (lane & 7) << 4, lhi = (lane >> 4) << 4, lsw2 = (lane & 6) << 3; \
    (void)g; (void)t; (void)srowoff; (void)lsw; (void)lhi; (void)lsw2;
    uint32_t stgp = 0, peer;
    asm volatile("mapa.shared::cluster.u32 %0, %1, %2;" : "=r"(peer) : "r"(sbase), "r"(rank ^ 1));
    peer -= sbase;
    const uint32_t dA0 = (((sbase & 0x3FFFF) + wg * 8192) >> 4) | 0x10000u, dB0 = ((sbase & 0x3FFFF) >> 4) | 0x2000000u;
    cluster_wait();
#define DESC(lo, hi) ((uint64_t)(uint32_t)(lo) | ((uint64_t)(hi) << 32))
#define STG_ARRIVE() { __syncwarp(); if (elect_one()) mbar_arrive_local(bar_stg); }
#define STG_WAIT() { mbar_wait(bar_stg, stgp); stgp ^= 1; }
#define PROFS() do {} while (0)
#define REL(addr) { if (elect_one()) { mbar_arrive_local(addr); asm volatile("mbarrier.arrive.shared::cluster.b64 _, [%0];" :: "r"((addr) + peer) : "memory"); } }
#define QSTEP(ACC, DA, SC) { \
      const uint32_t da = (DA), db = dB0 + (ub & 0x18) * (QST >> 7); \
      mbar_wait(ub, par); \
      wgmma_fence(); \
      wgmma4_n192<SC>(ACC, da, db); \
      wgmma_commit(); PROFS(); }
#define QREL() { wgmma_wait<1>(); REL(ub + 376); ub += 8; }
#define RA_CUR (dA0 + (OFF_RA >> 4) + (ub & 0x18) * (SLOT >> 7))
#define PUMP1() { QSTEP(S1, RA_CUR, 1); QREL(); }
#define PUMPN() { wgmma_fence(); wgmma4_n192<1>(S1, RA_CUR, dB0 + (ub & 0x18) * (QST >> 7)); wgmma_commit(); PROFS(); QREL(); }
#define PUMP0() { PUMP1(); SCHED_FENCE(); }
#define WSTEP() { \
      const uint32_t s4 = (ub - bar_full - 256) >> 1; \
      const uint32_t da = dA0 + (((uint32_t)(WO_ASLOT(par) >> s4) & 15) << 10), db = dB0 + (((uint32_t)(WO_BSLOT >> s4) & 15) << 10); \
      mbar_wait(ub, par); \
      wgmma_fence(); \
      wgmma4_n128<1>(S1, da, db); \
      wgmma_commit(); PROFS(); \
      wgmma_wait<1>(); \
      if (s4) REL(ub + 376); \
      ub += 8; }
#define PUMPS(n) { _Pragma("unroll 1") for (int i_ = 0; i_ < (n); i_++) PUMP1(); }
#define LNSTEP(ACC, hh) { wgmma_fence(); wgmma_n192<1, 0>(ACC, make_desc(sbase + OFF_LNA + wg * 1024, 0, 128) ^ (1ull << 62), make_desc(sbase + OFF_LNB + (hh) * 4096, 0, 128) ^ (1ull << 62)); }
#define WARP_STORE(tm, tile, col, row) { fence_proxy_async_smem(); __syncwarp(); \
      if (elect_one()) { tma_store_2d(tm, (tile) + r0 * 128, col, (row) + r0); asm volatile("cp.async.bulk.commit_group;" ::: "memory"); } __syncwarp(); }
#define TILE_CONSTS(base, on, bit) \
      uint32_t ta[5]; \
      { PMASKS(on, bit); (void)pbit; ta[4] = pm0; } \
      _Pragma("unroll") for (int j = 0; j < 4; j++) ta[j] = (base) + srowoff + ((((uint32_t)j << 5) + lhi) ^ lsw); \
      PINU(ta, 5); SCHED_FENCE(); \
      const uint32_t pm0 = ta[4], pbit = (bit)
#define X_OUT(pc, W) { \
      _Pragma("unroll") for (int j = 0; j < 4; j++) \
        stsm_x4(ta[j] + (pc) * SLOT, \
                PBIT(pack_bf16((W)[j * 8 + 0], (W)[j * 8 + 1])), PBIT(pack_bf16((W)[j * 8 + 2], (W)[j * 8 + 3])), \
                (pack_bf16((W)[j * 8 + 4], (W)[j * 8 + 5])), (pack_bf16((W)[j * 8 + 6], (W)[j * 8 + 7]))); }
#define REST_P1(SKEW) { \
      mbar_wait(bar_stat2, par); \
      LNSTEP(S1, 1); \
      wgmma_commit(); \
      _Pragma("unroll 1") while (ub < bar_full + 256) { \
        const bool hold = ub == bar_full + 256 - 8 * (SKEW) && wg == 0; \
        if (hold) { wgmma_wait<0>(); REL(ub + 376); bar_sync<BAR_SKEW, 256>(); } \
        QSTEP(S1, RA_CUR, 1); \
        if (ub == bar_full + 248 && wg == 1) bar_arrive<BAR_SKEW, 256>(); \
        wgmma_wait<1>(); if (!hold) REL(ub + 376); ub += 8; \
      } \
      mbar_wait(bar_done + (31 - (SKEW)) * 8, par);        \
      wgmma_wait<0>(); \
      ACC_FENCE(S1, 96); \
      REL(bar_done + 31 * 8); \
      PROF(13); }
#define FOLD(tile, rd) { \
          LANE_CONSTS(); \
          float d[32]; \
          ACC_DEF(d, 32); \
          mbar_wait(bar_phi, 0); \
          wgmma_fence(); \
          _Pragma("unroll") for (int i = 0; i < 2; i++) { \
            const uint64_t da = make_desc((tile) + wg * 8192 + i * 64, 16, 1024); \
            const uint64_t db = make_desc(sbase + OFF_PHI + wg * 4096 + i * 2048, 16, 512) ^ (3ull << 62); \
            wgmma_n32<0>(d + i * 16, da, db); wgmma_n32<1>(d + i * 16, da + 2, db + 64); \
          } \
          wgmma_commit(); \
          PUMP0(); \
          ACC_FENCE(d, 32); \
          bar_wg(wg); \
          _Pragma("unroll") for (int i = 0; i < 4; i++) { \
            const float* x = d + (i & 1) * 8 + (i >> 1) * 2; \
            if (rd) sts128((tile) + wg * 8192 + ((warp & 3) * 16 + (i >> 1) * 8 + g) * 128 + (((2 * t + (i & 1)) ^ g) << 4), \
                           pack_bf16(x[0], x[1]), pack_bf16(x[4], x[5]), pack_bf16(x[16], x[17]), pack_bf16(x[20], x[21])); \
            else stsm_x4((tile) + srowoff + ((((uint32_t)i << 5) + lhi) ^ lsw), pack_bf16(d[i * 8], d[i * 8 + 1]), pack_bf16(d[i * 8 + 2], d[i * 8 + 3]), \
                         pack_bf16(d[i * 8 + 4], d[i * 8 + 5]), pack_bf16(d[i * 8 + 6], d[i * 8 + 7])); \
          } \
          }
#define XM_ISSUE() { mbar_wait(bar_xr, par); wgmma_fence(); \
      wgmma_copy(T_, dA0 + (OFF_RA >> 4), make_desc(sbase + OFF_ID, 128, 128) ^ (1ull << 62)); }
#define COPYN(d, s, n) _Pragma("unroll") for (int i_ = 0; i_ < (n); i_++) { uint32_t c_; asm volatile("mov.b32 %0, %1;" : "=r"(c_) : "f"((s)[i_])); (d)[i_] = __uint_as_float(c_); }
#define COPY64(d, s) COPYN(d, s, 64)
#define XM_DONE() { ACC_FENCE(T_, 64); COPY64(S1, T_); ACC_FENCE(S1, 64); \
      __syncwarp(); if (elect_one()) mbar_arrive_local(bar_lx); }
#define LOAD_X() { float T_[64]; ACC_DEF(T_, 64); wgmma_wait<0>(); XM_ISSUE(); wgmma_commit(); wgmma_wait<0>(); XM_DONE(); }

    float S0[96], S1[96];
#define FIRST_STEP(l_) { const int ln_ = (l_), l = ln_; const uint32_t ub = bar_full; (void)l; (void)ub; ACC_DEF(S0, 96); wgmma_fence(); wgmma4_n192<0>(S0, dA0 + (OFF_S >> 4), dB0); wgmma_commit(); PROFS(); }
    mbar_wait(bar_full, 0);
    FIRST_STEP(0);
    LOAD_EPOCH();
#pragma unroll 1
    for (int l = 0;; l++) {
      const uint32_t par = l & 1;
      uint32_t ub = bar_full + 8;
      PROF(1);
      {
        LANE_CONSTS();
        uint32_t ta[4];
#pragma unroll
        for (int j = 0; j < 4; j++) ta[j] = pK + srowoff + ((((uint32_t)j << 5) + lhi) ^ lsw);
        float p0, p1, a0 = 0.f, a1 = 0.f, q0 = 0.f, q1 = 0.f;
#define STATS(j0, j1) _Pragma("unroll") for (int j = (j0); j < (j1); j++) { \
          uint32_t x[4]; \
          ldsm_x4(ta[j & 3] + (j >> 2) * SLOT, x[0], x[1], x[2], x[3]); \
          if (j == 0) { p0 = __shfl_sync(0xffffffffu, bf_lo(x[0]), lane & 28); p1 = __shfl_sync(0xffffffffu, bf_lo(x[1]), lane & 28); } \
          _Pragma("unroll") for (int i = 0; i < 4; i += 2) { \
            const float d0 = bf_lo(x[i]) - p0, d1 = bf_hi(x[i]) - p0, d2 = bf_lo(x[i + 1]) - p1, d3 = bf_hi(x[i + 1]) - p1; \
            a0 += d0 + d1; a1 += d2 + d3; \
            q0 = fmaf(d1, d1, fmaf(d0, d0, q0)); q1 = fmaf(d3, d3, fmaf(d2, d2, q1)); } } \
          asm volatile("" : "+f"(a0), "+f"(a1), "+f"(q0), "+f"(q1), "+f"(p0), "+f"(p1)); SCHED_FENCE()
        if (SB0) { STATS(0, SB0); }
        bar_wg(wg);
        QSTEP(S0, dA0 + ((OFF_S + SLOT) >> 4), 1);
        QREL();
        SCHED_FENCE();
        STATS(SB0, SB1);
        ACC_DEF(S1, 96);
        QSTEP(S1, dA0 + (OFF_S >> 4), 0);
        QREL();
        SCHED_FENCE();
        STATS(SB1, SB2);
        QSTEP(S1, dA0 + ((OFF_S + SLOT) >> 4), 1);
        QREL();
        SCHED_FENCE();
        STATS(SB2, 8);
#pragma unroll
        for (int o = 1; o <= 2; o <<= 1) {
          a0 += __shfl_xor_sync(0xffffffffu, a0, o); a1 += __shfl_xor_sync(0xffffffffu, a1, o);
          q0 += __shfl_xor_sync(0xffffffffu, q0, o); q1 += __shfl_xor_sync(0xffffffffu, q1, o);
        }
        if (t == 1) { a0 = a1; q0 = q1; p0 = p1; }
        if (t < 2) st_b64(g_stats + (size_t)(mm * 128 + r0 + g + t * 8) * 8 + jj, __float_as_uint(fmaf(a0, 1.f / 128.f, p0)),
                          (__float_as_uint(fmaxf(fmaf(a0 * (-1.f / 128.f), a0, q0), 0.f)) & ~3u) | STAT_TAG(l));
        if (l) { asm volatile("cp.async.bulk.wait_group 0;" ::: "memory"); bar_arrive<BAR_X1, 288>(); }
#pragma unroll 1
        for (int i = 0; i < 14; i++) {
          QSTEP(S0, RA_CUR, 1);
          if (i == 0) PROF(2);
          QREL();
        }
      }
      LANE_CONSTS();
      mbar_wait(bar_stat, par);
      LNSTEP(S0, 0);
      wgmma_commit();
      const float rs0 = lds32f(sbase + OFF_ST + (r0 + g) * 4), rs1 = lds32f(sbase + OFF_ST + (r0 + g + 8) * 4);
      PUMP0();
      ACC_FENCE(S0, 96);
      PROF(3);
      if (!par) {
        constexpr uint32_t par = 0;
        uint32_t qa[16];
        uint32_t kf[24], vf[24];
#define DRAIN_A(ACC, hp, PMP) { \
          LANE_CONSTS(); \
          FRAG(kf, ACC + 32, 0, (hp) * 2); \
          PMP; \
          FRAG(vf, ACC + 64, 1, (hp) * 2 + 1); \
          _Pragma("unroll") for (int i_ = 0; i_ < 16; i_++) qa[i_] = pack_bf16(ACC[2 * i_], ACC[2 * i_ + 1]); \
          PINU(qa, 16); }
        DRAIN_A(S0, 0, PUMP0());
        if (l == 0 && NLAYERS > 1) {
#pragma unroll 1
          for (int rd = 1; rd >= 0; rd--) {
            FOLD(sbase + (12 - rd) * SLOT, rd);
            fence_proxy_async_smem();
            asm volatile("bar.arrive %0, 288;" :: "r"(BAR_WF + 1 - rd) : "memory");
          }
        }
        PUMPS(FPUMP);
#pragma unroll 1
        for (int h = 0; h < 2; h++) {
          PROFH(4, 16);
          LANE_CONSTS();
          FRAG_PUT(kf + 16, 0); FRAG_PUT(vf + 16, 1);
          STG_ARRIVE();
          if (h) { PROF(8); LOAD_X(); PROF(9); WSTEP(); PROF(10); } else PUMPS(HPUMP2);
          const bool gt0 = 2 * t > g, gt1 = 2 * t >= g;
          uint32_t msk[2] = {(gt0 ? 0xFFFFu : 0u) | (gt1 ? 0xFFFF0000u : 0u), g == 2 * t ? 0x10001u : 0u};
          PINU(msk, 2);
          TILE_CONSTS(sbase, false, 0);
          (void)pm0; (void)pbit;
          if (h) PROF(12);
          STG_WAIT();
          if (h) PROF(14);
          if (warp < 2) mbar_wait(bar_halo, h);
          if (h) PROF(15);
          if (h == 0) mbar_wait(ub, par);
          FRAG_GET(kf, 0);
          PROFH(5, 17);
          float s[2][3][4];
#pragma unroll
          for (int ks = 0; ks < 2; ks++)
#pragma unroll
            for (int i = 0; i < 6; i++) {
              const int hh = i & 1, jb = 2 - (i >> 1);
              const uint32_t* b = kf + jb * 8 + hh * 4 + ks * 2;
              if (ks) mma_bf16(s[hh][jb], qa[hh * 8 + 4], qa[hh * 8 + 5], qa[hh * 8 + 6], qa[hh * 8 + 7], b[0], b[1]);
              else mma_bf16_z(s[hh][jb], qa[hh * 8], qa[hh * 8 + 1], qa[hh * 8 + 2], qa[hh * 8 + 3], b[0], b[1]);
            }
          if (h == 0) PUMPN()
          PROFH(6, 18);
          float va[2][2], vb[2][2], mx[2][2];
#pragma unroll
          for (int hh = 0; hh < 2; hh++) {
            va[hh][0] = gt0 ? s[hh][0][0] : s[hh][1][0];
            vb[hh][0] = gt1 ? s[hh][0][1] : s[hh][1][1];
            va[hh][1] = gt0 ? s[hh][1][2] : s[hh][2][2];
            vb[hh][1] = gt1 ? s[hh][1][3] : s[hh][2][3];
          }
          if (warp < 2 && mm == 0) {
#pragma unroll
            for (int hh = 0; hh < 2; hh++) { if (gt0) va[hh][0] = -INFINITY; if (gt1) vb[hh][0] = -INFINITY; }
          }
#pragma unroll
          for (int i = 0; i < 4; i++) mx[i >> 1][i & 1] = fmaxf(va[i >> 1][i & 1], vb[i >> 1][i & 1]);
#pragma unroll
          for (int o = 1; o <= 2; o <<= 1)
#pragma unroll
            for (int i = 0; i < 4; i++) mx[i >> 1][i & 1] = fmaxf(mx[i >> 1][i & 1], __shfl_xor_sync(0xffffffffu, mx[i >> 1][i & 1], o));
          const float sc0 = rs0 * (0.17677669529663687f * LOG2E), sc1 = rs1 * (0.17677669529663687f * LOG2E);
#pragma unroll
          for (int i = 0; i < 4; i++) {
            const float sc = (i & 1) ? sc1 : sc0, m = mx[i >> 1][i & 1];
            va[i >> 1][i & 1] = ex2((va[i >> 1][i & 1] - m) * sc); vb[i >> 1][i & 1] = ex2((vb[i >> 1][i & 1] - m) * sc);
            mx[i >> 1][i & 1] = va[i >> 1][i & 1] + vb[i >> 1][i & 1];
          }
          if (h == 0) { PIN(&va[0][0], 4); PIN(&vb[0][0], 4); PIN(&mx[0][0], 4); PUMP1(); }
          if (h) PROF(20);
          if (warp < 2) mbar_wait(bar_halo + 8, h);
          if (h) PROF(21);
          if (h == 0) mbar_wait(ub, par);
          FRAG_GET(vf, 1);
#pragma unroll
          for (int o = 1; o <= 2; o <<= 1)
#pragma unroll
            for (int i = 0; i < 4; i++) mx[i >> 1][i & 1] += __shfl_xor_sync(0xffffffffu, mx[i >> 1][i & 1], o);
          float o[8][4];
          uint32_t pa[4][2];
#pragma unroll
          for (int i = 0; i < 4; i++) {
            const float iv = rcp_fast(mx[i >> 1][i & 1]);
            const uint32_t w = pack_bf16(va[i >> 1][i & 1] * iv, vb[i >> 1][i & 1] * iv);
            pa[i][0] = w & msk[0]; pa[i][1] = w & ~msk[0];
          }
          PROFH(7, 19);
#pragma unroll
          for (int i = 7; i >= 0; i--) {
            const uint32_t* a = vf + (i >> 2) * 8 + (i & 3) * 2;
            mma_bf16_z(o[i], a[0], a[1], a[8], a[9], pa[(i & 2) + (i >> 2)][0], pa[(i & 2) + (i >> 2)][1]);
          }
          if (h == 0) PUMPN() else mbar_wait(bar_done + 30 * 8, par);
          if (NLAYERS > 1 && l + h == 0) mbar_wait(bar_phi + 8, 0);
          if (h) PROF(22);
          {
            const uint32_t pm0 = msk[1], pbit = O_BIT(l) * 0x10001u;
#pragma unroll
            for (int i = 0; i < 4; i++)
              stsm_x4_t(ta[i] + (h ? 3 : 12) * SLOT, PBIT(pack_bf16(o[i][0], o[i][1])), PBIT(pack_bf16(o[i + 4][0], o[i + 4][1])),
                        pack_bf16(o[i][2], o[i][3]), pack_bf16(o[i + 4][2], o[i + 4][3]));
          }
          WARP_STORE(&tm_os, sbase + (h ? 3 : 12) * SLOT, jj * 128 + h * 64, mm * 128);
          PROFH(11, 23);
          if (h) break;
          REST_P1(ASKEW);
          asm volatile("cp.async.bulk.wait_group.read 0;" ::: "memory");
          DRAIN_A(S1, 1, {});
        }
      } else {
        constexpr uint32_t par = 1;
        float st[32];
        const float c0 = rs0 * LOG2E, c1 = rs1 * LOG2E;
        { V_ADDR(pV, 0); STAGE_V(S0 + 64); }
        if (warp < 2) sts128(sbase + OFF_ONES + warp * 512 + lane * 16, 0x3F803F80u, 0x3F803F80u, 0x3F803F80u, 0x3F803F80u);
        scale32(st, S0, c0, c1);
        PIN(st, 32);
#define PHI_PIECE(c) { \
          e_[2 * (c)] = ex2(st[2 * (c)]); e_[2 * (c) + 1] = ex2(st[2 * (c) + 1]); \
          _Pragma("unroll") for (int k_ = 4 * (c); k_ < 4 * (c) + 4; k_++) m_[(c) >> 1] = (k_ & 7) ? fmaf(st[k_], st[k_], m_[(c) >> 1]) : st[k_] * st[k_]; \
          asm volatile("" : "+f"(e_[2 * (c)]), "+f"(e_[2 * (c) + 1]), "+f"(m_[(c) >> 1])); SCHED_FENCE(); }
#define PHI_FIN() { \
          big = __any_sync(0xffffffffu, !(fmaxf(fmaxf(m_[0], m_[1]), fmaxf(m_[2], m_[3])) < BIGLIM)); \
          if (__builtin_expect(big, 0)) { COPYN(e_, st, 16); } \
          _Pragma("unroll") for (int k_ = 0; k_ < 16; k_++) st[k_] = e_[k_]; \
          PIN(st, 16); }
#define KV_MMA(vs, IL) { \
          const uint32_t dp = dA0 + 12 * 1024 - wg * 2560, dv = dA0 + (vs) * 1024 + ((OFF_ONES - (vs) * SLOT - 16) << 12) - wg * (512 << 16); \
          STG_WAIT(); \
          wgmma_fence(); \
          _Pragma("unroll") for (int ks = 0; ks < 8; ks++) { \
            const uint64_t a = DESC(dp + ks * 128, 0x40000040), b = DESC(dv + ks * (64 - (64 << 16)), 0x80000020); \
            if ((IL) && ks) wgmma_fence(); \
            if (ks == 0) wgmma_n40<0, 1>(kv, a, b); else wgmma_n40<1, 1>(kv, a, b); \
            if (ks == 7) wgmma_commit(); \
            if (IL) PHI_PIECE(ks); } }
#define KV_RED1(i) if (h) red_v4(g_kv[l >> 1] + (jj * 4) * KVH + warp * 768 + lane * 4 + (i) * 128, S0[32 + (i) * 3], S0[33 + (i) * 3], S0[34 + (i) * 3], 1.f)
#define KV_REDS(n) { _Pragma("unroll") for (int i_ = 0; i_ < 6; i_++) if (((RPACE >> (4 * i_)) & 15) == (n)) KV_RED1(i_); }
#define KV_SEND(kp) { \
          float sd[9]; \
          _Pragma("unroll") for (int i = 0; i < 8; i++) { (kp)[i] = kv[i]; sd[i] = kv[8 + i]; } \
          (kp)[8] = rank ? kv[18] : kv[16]; sd[8] = rank ? kv[16] : kv[18]; \
          const uint32_t ra = sbase + peer + (warp * 32 + lane) * 4, rb = bar_kx + peer; \
          if (elect_one()) mbar_expect_tx(bar_kx, 1152); \
          _Pragma("unroll") for (int i = 0; i < 2; i++) \
            asm volatile("st.async.weak.shared::cluster.mbarrier::complete_tx::bytes.v4.f32 [%0], {%1, %2, %3, %4}, [%5];" \
                         :: "r"(ra + (warp * 32 + lane) * 12 + OFF_PHI + i * 4096), "f"(sd[4 * i]), "f"(sd[4 * i + 1]), "f"(sd[4 * i + 2]), "f"(sd[4 * i + 3]), "r"(rb) : "memory"); \
          asm volatile("st.async.weak.shared::cluster.mbarrier::complete_tx::bytes.f32 [%0], %1, [%2];" :: "r"(ra + OFF_LNB), "f"(sd[8]), "r"(rb) : "memory"); }
#define KV_RECV(kp, hp) { \
          float r_[9]; \
          float* kvg = g_kv[l >> 1] + (jj * 4 + (hp) * 2) * KVH + warp * 768 + rank * 384 + lane * 4; \
          mbar_wait(bar_kx, l >> 1); \
          _Pragma("unroll") for (int i = 0; i < 2; i++) \
            asm volatile("ld.shared.v4.f32 {%0, %1, %2, %3}, [%4];" : "=f"(r_[4 * i]), "=f"(r_[4 * i + 1]), "=f"(r_[4 * i + 2]), "=f"(r_[4 * i + 3]) \
                         : "r"(sbase + OFF_PHI + i * 4096 + (warp * 32 + lane) * 16) : "memory"); \
          r_[8] = lds32f(sbase + OFF_LNB + (warp * 32 + lane) * 4); \
          _Pragma("unroll") for (int i = 0; i < 3; i++) red_v4(kvg + i * 128, (kp)[3 * i] + r_[3 * i], (kp)[3 * i + 1] + r_[3 * i + 1], (kp)[3 * i + 2] + r_[3 * i + 2], 2.f); }
#define KV_LOAD(hp) { \
          const uint4* kvg = reinterpret_cast<const uint4*>(g_kv[l >> 1] + (jj * 4 + (hp) * 2) * KVH) + warp * 192 + lane; \
          _Pragma("unroll") for (int i = 0; i < 6; i++) v[i] = ld_b128(kvg + i * 32); }
#define KVV(i) __uint_as_float((i) % 3 == 0 ? v[(i) / 3].x : ((i) % 3 == 1 ? v[(i) / 3].y : v[(i) / 3].z))
#define KV_TILE(hp) { \
          _Pragma("unroll 1") for (int it = 0; it < (1 << 16); it++) { \
            if (__all_sync(0xffffffffu, (v[0].w & v[1].w & v[2].w & v[3].w & v[4].w & v[5].w) == 0x41800000u)) break; \
            RETRY_COUNT(); \
            KV_LOAD(hp); \
          } \
          if (hp) PROF(26); else PROF(25); \
          const uint32_t e = lane & 7, jt = ((lane >> 1) & 4) + (e >> 1); \
          const uint32_t row = ((((warp >> 1) ^ wg) & 1) << 5) + ((jt & 1) << 4) + ((warp & 1) << 3) + (jt & 6) + (e & 1); \
          const uint32_t kd = pV + wg * 8192 + row * 128, ksw = (row & 7) << 4; \
          _Pragma("unroll") for (int i = 0; i < 2; i++) \
            stsm_x4(kd + ((i * 32 + lhi) ^ ksw), pack_bf16(KVV(i * 9), KVV(i * 9 + 1)), pack_bf16(KVV(i * 9 + 2), KVV(i * 9 + 3)), \
                    pack_bf16(KVV(i * 9 + 4), KVV(i * 9 + 5)), pack_bf16(KVV(i * 9 + 6), KVV(i * 9 + 7))); \
          stsm_x4(kd + ((64u + lhi) ^ ksw), pack_bf16(KVV(8), 1.f), pack_bf16(KVV(17), 1.f), 0u, 0u); }
#pragma unroll 1
        for (int h = 0; h < 2; h++) {
          PROFH(4, 6);
          PUMP0();
          LANE_CONSTS();
          const uint32_t dsw = (uint32_t)(g ^ (2 * t)) << 4, dst = ((t & 2) ? pK : sbase + 12 * SLOT) + (r0 + g) * 128;
          float e[16], f[16];
          KV_REDS(1);
          float sa = exps16_<0>(e, st);
          exps16_fix<0>(e, st, sa);
          asm volatile("" : "+f"(sa)); PIN(e, 16); PUMP0();
          if (h) STG_WAIT();
          KV_REDS(2);
          store16(e, sa, dst, dsw, 4);
          float sb = exps16_<1>(f, st);
          exps16_fix<1>(f, st, sb);
          asm volatile("" : "+f"(sb)); PIN(f, 16); PUMP0();
          KV_REDS(3);
          store16(f, sb, dst, dsw, 0);
          float sc = exps16_<0>(e, st + 2);
          exps16_fix<0>(e, st + 2, sc);
          asm volatile("" : "+f"(sc)); PIN(e, 16); PUMP0();
          KV_REDS(4);
          store16(e, sc, dst + 1024, dsw, 4);
          float sd = exps16_<1>(f, st + 2);
          exps16_fix<1>(f, st + 2, sd);
          asm volatile("" : "+f"(sd)); PIN(f, 16); PUMP0();
          store16(f, sd, dst + 1024, dsw, 0);
          PROFH(5, 7);
          if (h) break;
          {
            float kv[20];
            ACC_DEF(kv, 20);
            fence_proxy_async_smem();
            STG_ARRIVE();
            float e_[16], m_[4];
            KV_MMA(11, 0);
            PUMP0();
            ACC_FENCE(kv, 20);
            STG_ARRIVE();
            scale32(st, S0 + 32, c0, c1);
            PIN(st, 32);
            {
              COPYN(S0 + 32, kv, 8); COPYN(S0 + 40, kv + 16, 1); COPYN(S0 + 41, kv + 8, 8); COPYN(S0 + 49, kv + 18, 1);
              const int h = 1;
              KV_REDS(0);
            }
          }
        }
        bool big;
        uint4 v[6];
        {
          float kv[20];
          { LANE_CONSTS(); KV_LOAD(0); }
          mbar_wait(bar_stat2, par);
          ub = bar_full + 240;
          LNSTEP(S1, 1);
          PUMP1();
          if (wg == 0) bar_sync<BAR_SKEW, 256>();
          QSTEP(S1, RA_CUR, 1);
          if (wg == 1) bar_arrive<BAR_SKEW, 256>();
          QREL();
          { LANE_CONSTS(); KV_TILE(0); }
          LANE_CONSTS();
          V_ADDR(sbase + 3 * SLOT, rank * 32);
          PINU(va_, 2);
          mbar_wait(bar_done + 30 * 8, par);
          wgmma_wait<0>();
          ACC_FENCE(S1, 96);
          PROF(13);
          STAGE_V(S1 + 64);
          fence_proxy_async_smem();
          STG_ARRIVE();
          REL(bar_done + 31 * 8);
          scale32(st, S1, c0, c1);
          PIN(st, 32);
          PROF(16);
          ACC_DEF(kv, 20);
          float e_[16], m_[4];
          KV_MMA(3, 1);
          SCHED_FENCE();
          PROF(14);
          PHI_FIN();
          SCHED_FENCE();
          PROF(15);
          wgmma_wait<0>();
          ACC_FENCE(kv, 20);
          PROF(12);
          { float kp[9]; KV_SEND(kp); _Pragma("unroll") for (int i = 0; i < 3; i++) v[i] = make_uint4(__float_as_uint(kp[3 * i]), __float_as_uint(kp[3 * i + 1]), __float_as_uint(kp[3 * i + 2]), 0u); }
          PROF(17);
        }
#pragma unroll 1
        for (int h = 0; h < 2; h++) {
          const uint32_t pO = sbase + (h ? 3 : 8) * SLOT;
          LANE_CONSTS();
          uint32_t fq[32];
          PROFH(18, 32);
          SCHED_FENCE();
          phiq_b<1>(fq, st, big); PINU(fq, 16); PIN(st + 16, 16);
          SCHED_FENCE();
          PROFH(8, 9);
          if (h) {
            asm volatile("cp.async.bulk.wait_group.read 0;" ::: "memory");
            mbar_wait(bar_lx, par);
            PROF(30);
            KV_TILE(1);
            fence_proxy_async_smem();
            STG_ARRIVE();
          }
          SCHED_FENCE();
          if (h == 0) {
            float kp[9];
#pragma unroll
            for (int i = 0; i < 9; i++) kp[i] = KVV(i);
            KV_RECV(kp, 1);
            SCHED_FENCE();
          }
          phiq_b<0>(fq + 16, st + 16, big); PINU(fq + 16, 16);
          PROFH(10, 21);
          if (h) STG_WAIT();
          wgmma_wait<0>();
          ACC_FENCE(S1, 64);
          PROFH(19, 33);
          float o[4][20];
#define O_MMA(hh) { \
            const uint64_t db = make_desc(pV + (hh) * 8192, 16, 1024); \
            ACC_DEF(o[(hh) * 2], 20); ACC_DEF(o[(hh) * 2 + 1], 20); \
            wgmma_fence(); \
            wgmma_n40_rs<0>(o[(hh) * 2], fq + (hh) * 16, db + 256); wgmma_n40_rs<0>(o[(hh) * 2 + 1], fq + (hh) * 16 + 8, db); \
            wgmma_n40_rs<1>(o[(hh) * 2], fq + (hh) * 16 + 4, db + 384); wgmma_n40_rs<1>(o[(hh) * 2 + 1], fq + (hh) * 16 + 12, db + 128); \
            wgmma_commit(); }
          O_MMA(0);
          SCHED_FENCE();
          PMASKS(true, O_BIT(l));
#pragma unroll
          for (int hh = 0; hh < 2; hh++) {
            wgmma_wait<0>();
            ACC_FENCE(o[hh * 2], 20); ACC_FENCE(o[hh * 2 + 1], 20);
            if (!hh) { O_MMA(1); SCHED_FENCE(); }
            if (hh) PROFH(22, 24);
            const float* x = o[hh * 2];
            const float* y = o[hh * 2 + 1];
            const float sx0 = x[17] * 0x1p-40f, sy0 = y[17] * 0x1p-40f, sx1 = x[19] * 0x1p-40f, sy1 = y[19] * 0x1p-40f;
            const float i0 = rcp_fast(fmaf(fmaf(x[17], 1e-6f, x[16]), sy0, y[16] * sx0)), i1 = rcp_fast(fmaf(fmaf(x[19], 1e-6f, x[18]), sy1, y[18] * sx1));
            const float ax0 = sy0 * i0, ay0 = sx0 * i0, ax1 = sy1 * i1, ay1 = sx1 * i1;
#pragma unroll
            for (int dp = 0; dp < 2; dp++)
              stsm_x4(pO + srowoff + ((hh * 64 + dp * 32 + lhi) ^ lsw),
                      PBIT(pack_bf16(fmaf(x[dp * 8], ax0, y[dp * 8] * ay0), fmaf(x[dp * 8 + 1], ax0, y[dp * 8 + 1] * ay0))),
                      PBIT(pack_bf16(fmaf(x[dp * 8 + 2], ax1, y[dp * 8 + 2] * ay1), fmaf(x[dp * 8 + 3], ax1, y[dp * 8 + 3] * ay1))),
                      (pack_bf16(fmaf(x[dp * 8 + 4], ax0, y[dp * 8 + 4] * ay0), fmaf(x[dp * 8 + 5], ax0, y[dp * 8 + 5] * ay0))),
                      (pack_bf16(fmaf(x[dp * 8 + 6], ax1, y[dp * 8 + 6] * ay1), fmaf(x[dp * 8 + 7], ax1, y[dp * 8 + 7] * ay1))));
          }
          WARP_STORE(&tm_os, pO, jj * 128 + h * 64, mm * 128);
          PROFH(20, 34);
          if (h) break;
          float T_[64];
          scale32(st, S1 + 32, c0, c1);
          PIN(st, 32);
          ACC_DEF(T_, 64);
          XM_ISSUE(); wgmma_commit();
          SCHED_FENCE();
          big = any_big(st);
          SCHED_FENCE();
          PROF(27);
          wgmma_wait<0>(); XM_DONE();
          PROF(28);
          bar_wg(wg);
          WSTEP();
          SCHED_FENCE();
          PROF(29);
          KV_LOAD(1);
          phiq_a(st, big); PIN(st, 16);
          PROF(31);
        }
      }
      __syncwarp();
      if (elect_one()) mbar_arrive_local(bar_epi);
      bar_wg(wg);
#pragma unroll 1
      while (ub < bar_full + 384) {
        WSTEP();
        if (ub == bar_full + 8 * 41) { asm volatile("cp.async.bulk.wait_group.read 0;" ::: "memory"); PROF(35); }
        if (ub == bar_full + 8 * 42) PROF(36);
      }
      {
        float Wb[32];
        LANE_CONSTS();
        TILE_CONSTS(pK, l < NLAYERS - 1, X_BIT(l));
        if (l < NLAYERS - 1) mbar_wait(bar_full, par ^ 1);
        wgmma_wait<0>();
        ACC_FENCE(S1, 64);
        COPYN(Wb, S1 + 32, 32);
        PROF(37);
        X_OUT(0, S1);
        WARP_STORE(l < NLAYERS - 1 ? &tm_os : &tm_xo, pK, jj * 128 + (l < NLAYERS - 1 ? 0 : (warp & 1) * 1024), l < NLAYERS - 1 ? mm * 128 + S_LEN : mm * 64 + (warp >> 1) * 16 - r0);
        if (l == NLAYERS - 1) { PMASKS(false, 0); X_OUT(1, Wb); break; }
        PROF(38);
        bar_wg(wg);
        FIRST_STEP(l + 1);
        REL(bar_done + 47 * 8);
        PROF(39);
        { PMASKS(false, 0); X_OUT(1, Wb); }
        fence_proxy_async_smem();
      }
    }
    WARP_STORE(&tm_xo, pV, jj * 128 + 64 + (warp & 1) * 1024, mm * 64 + (warp >> 1) * 16 - r0);
    asm volatile("cp.async.bulk.wait_group.read 0;" ::: "memory");
    cluster_sync();
  }
}

typedef CUresult (*PFN_encode)(CUtensorMap*, CUtensorMapDataType, cuuint32_t, void*, const cuuint64_t*, const cuuint64_t*,
                               const cuuint32_t*, const cuuint32_t*, CUtensorMapInterleave, CUtensorMapSwizzle,
                               CUtensorMapL2promotion, CUtensorMapFloatOOBfill);

CUtensorMap make_map(PFN_encode enc, const void* ptr, uint64_t inner, uint64_t outer, uint32_t box_inner, uint32_t box_outer,
                     CUtensorMapSwizzle swz = CU_TENSOR_MAP_SWIZZLE_128B, int promo = CU_TENSOR_MAP_L2_PROMOTION_L2_256B) {
  CUtensorMap m;
  cuuint64_t dims[2] = {inner, outer};
  cuuint64_t strides[1] = {inner * 2};
  cuuint32_t box[2] = {box_inner, box_outer};
  cuuint32_t es[2] = {1, 1};
  enc(&m, CU_TENSOR_MAP_DATA_TYPE_BFLOAT16, 2, const_cast<void*>(ptr), dims, strides, box, es, CU_TENSOR_MAP_INTERLEAVE_NONE,
      swz, (CUtensorMapL2promotion)promo, CU_TENSOR_MAP_FLOAT_OOB_FILL_NONE);
  return m;
}

CUtensorMap make_tile_map(PFN_encode enc, const void* ptr, uint64_t rows, bool by_parity, int promo) {
  CUtensorMap m;
  cuuint64_t dims[4] = {D_MODEL, 16, 2, rows / 32};
  cuuint64_t strides[3] = {by_parity ? 4096u : 2048u, by_parity ? 2048u : 32768u, 65536};
  cuuint32_t box[4] = {64, 16, 2, 4};
  cuuint32_t es[4] = {1, 1, 1, 1};
  enc(&m, CU_TENSOR_MAP_DATA_TYPE_BFLOAT16, 4, const_cast<void*>(ptr), dims, strides, box, es, CU_TENSOR_MAP_INTERLEAVE_NONE,
      CU_TENSOR_MAP_SWIZZLE_128B, (CUtensorMapL2promotion)promo, CU_TENSOR_MAP_FLOAT_OOB_FILL_NONE);
  return m;
}

}

extern "C" void kernel_launch(void* const* d_in, const int* in_sizes, int n_in, void* d_out, int out_size) {
  (void)in_sizes; (void)n_in; (void)out_size;
  static PFN_encode enc = nullptr;
  if (!enc) {
    void* fn = nullptr;
    cudaDriverEntryPointQueryResult qr;
    cudaGetDriverEntryPoint("cuTensorMapEncodeTiled", &fn, cudaEnableDefault, &qr);
    enc = (PFN_encode)fn;
    cudaFuncSetAttribute(mega_kernel, cudaFuncAttributeMaxDynamicSharedMemorySize, SMEM_BYTES);
  }
  Params prm;
  prm.x0 = (const __nv_bfloat16*)d_in[0];
  prm.wA_qkv = (const __nv_bfloat16*)d_in[1];
  prm.wA_o = (const __nv_bfloat16*)d_in[2];
  prm.wB_qkv = (const __nv_bfloat16*)d_in[4];
  prm.wB_phi = (const __nv_bfloat16*)d_in[5];
  prm.wB_o = (const __nv_bfloat16*)d_in[6];
  prm.out = (__nv_bfloat16*)d_out;
  void *obuf = nullptr, *wf = nullptr;
  cudaGetSymbolAddress(&obuf, g_obuf);
  cudaGetSymbolAddress(&wf, g_wfold);
  CUtensorMap tm_x0 = make_tile_map(enc, d_in[0], S_LEN, true, XPROMO);
  CUtensorMap tm_xo = make_map(enc, d_out, 2 * D_MODEL, S_LEN / 2, 64, 16);
  CUtensorMap tm_os = make_map(enc, obuf, D_MODEL, 2 * S_LEN, 64, 16);
  CUtensorMap tm_o = make_tile_map(enc, obuf, 2 * S_LEN, false, OPROMO);
  CUtensorMap tm_wf = make_map(enc, wf, 2048, D_MODEL, 64, 32);
  CUtensorMap tm_wqA = make_map(enc, d_in[1], 3 * D_MODEL, D_MODEL, 64, 32, CU_TENSOR_MAP_SWIZZLE_128B, WPROMO);
  CUtensorMap tm_wqB = make_map(enc, prm.wB_qkv, 3 * D_MODEL, D_MODEL, 64, 32);
  CUtensorMap tm_woA = make_map(enc, prm.wA_o, D_MODEL, D_MODEL, 64, 64);
  CUtensorMap tm_woB = make_map(enc, prm.wB_o, D_MODEL, D_MODEL, 64, 64);
  CUtensorMap tm_phi = make_map(enc, prm.wB_phi, 32, 1024, 32, 128, CU_TENSOR_MAP_SWIZZLE_64B);
  mega_kernel<<<NMAIN + NAUX, 384, SMEM_BYTES>>>(tm_x0, tm_xo, tm_os, tm_o, tm_wf, tm_wqA, tm_wqB, tm_woA, tm_woB, tm_phi, prm);
}
```

```cpp
#include <cuda_runtime.h>
#include <cuda.h>
#include <cuda_bf16.h>
#include <stdint.h>

#define NLAYERS 4

#define HPUMP2 1
#define ASKEW 2
#define FPUMP 3
#define PFGAP 100
#define POLLGAP 120
#define HW1 29
#define XPACE 0x06050401000000ull
#define XP0 4
#define HW0 18
#define XD 4
#define WFGAP 50
#define EARLY 2
#define BIGLIM 3600.f
#define SUMLO 0x1p-100f
#define SUMHI 0x1p100f
#define XPROMO 2
#define OPROMO 3
#define STAG2 300
#define WPROMO 3
#define SB0 2
#define SB1 4
#define SB2 6
#define PROWS 3
#define SPD0 0
#define SPD1 0
#define SPD2 300
#define FRB 0x3535353535ull
#define NOB 0xFFFFFF00u
#define NO1 ~0u
#define NOX ~0u
#define FD0 0
#define FD1 3
#define RPACE 0x221100
namespace {

constexpr int S_LEN = 2048, D_MODEL = 1024;
constexpr int NAUX = 4, NMAIN = 128;
constexpr int SLOT = 16384;
constexpr int QST = 24576;
constexpr int OFF_RA = 6 * SLOT, OFF_S = 10 * SLOT;
constexpr int OFF_HALO = 13 * SLOT, OFF_LNB = OFF_HALO  , OFF_ONES = OFF_HALO + 3072;
constexpr int OFF_ST = OFF_HALO + 7168  , OFF_ID = OFF_HALO + 7680, OFF_PHI = OFF_HALO + 8192;
constexpr int OFF_BAR = 14 * SLOT;
constexpr int OFF_LNA = OFF_BAR + 1024;
constexpr int SMEM_BYTES = OFF_LNA + 2048;
#define WO_ASLOT(par) ((par) ? 0x9876CAB39876CA98ull : 0xBC7698A3BC7698BCull)
constexpr unsigned long long WO_BSLOT = 0x5432105421054210ull;
__device__ __forceinline__ int srcb(int j, int i) { return (i + (i >= j)) & 7; }
__device__ __forceinline__ int kslice(int j, int i) { return i < 2 ? 2 * j + i : (i < 9 ? 2 * srcb(j, i - 2) : 2 * srcb(j, i - 9) + 1); }
__device__ __forceinline__ int wslice(int j, int s) { return 2 * ((s & 7) ? srcb(j, (s & 7) - 1) : j) + (s >> 3); }
constexpr int KVH = 6 * 128 * 4;

struct __align__(128) Flag { unsigned v; unsigned pad[31]; };
struct Flags {
  Flag xready[4][16];
  Flag wfready[8];
  Flag done;
  Flag epoch;
};

__device__ Flags g_flags;
__device__ __nv_bfloat16 g_obuf[2 * S_LEN * D_MODEL];
#define O_BIT(l) ((epoch * NLAYERS + (l) + 1) & 1u)
#define X_BIT(l) ((epoch * (NLAYERS - 1) + (l) + 1) & 1u)
__device__ __nv_bfloat16 g_wfold[D_MODEL * 2048];
__device__ uint4 g_halo[16 * 8 * 512];
__device__ __align__(128) float g_kv[2][32 * KVH];
__device__ __align__(128) uint2 g_colsum[2][1536][2];
__device__ __align__(128) uint2 g_stats[S_LEN * 8];
#define H_BIT(l) (NLAYERS > 2 ? (uint32_t)((l) == 0) : (ep1 & 1))
#define STAT_TAG(l) ((ep1 * NLAYERS + (l) + 1) & 3u)

#define RETRY_COUNT()
#define PRL 0
#define PRU 0
#define PROFL 1
#define PROFW 0
#define PROFT(i) do {} while (0)
#define PROF(i) do {} while (0)
#define PROFH(i, j) do {} while (0)

__device__ __forceinline__ uint32_t smem_u32(const void* p) { return (uint32_t)__cvta_generic_to_shared(p); }
__device__ __forceinline__ bool elect_one() {
  uint32_t p;
  asm volatile("{\n.reg .pred p;\nelect.sync _|p, 0xffffffff;\nselp.u32 %0, 1, 0, p;\n}\n" : "=r"(p));
  return p != 0;
}
__device__ __forceinline__ void mbar_init(uint32_t bar, uint32_t cnt) {
  asm volatile("mbarrier.init.shared::cta.b64 [%0], %1;" :: "r"(bar), "r"(cnt));
}
__device__ __forceinline__ void mbar_expect_tx(uint32_t bar, uint32_t bytes) {
  asm volatile("mbarrier.arrive.expect_tx.shared::cta.b64 _, [%0], %1;" :: "r"(bar), "r"(bytes) : "memory");
}
#define mbar_wait(bar, parity) \
  asm volatile("{\n.reg .pred p, q;\nW_%=:\nmbarrier.try_wait.parity.shared::cta.b64 p, [%1], %2;\nadd.s32 %0, %0, -1;\n" \
               "setp.gt.and.s32 q, %0, 0, !p;\n@q bra.uni W_%=;\n}\n" : "+r"(budget) : "r"((uint32_t)(bar)), "r"((uint32_t)(parity)) : "memory")
#define mbar_wait_sl(bar, parity) \
  asm volatile("{\n.reg .pred p, q;\nW_%=:\nmbarrier.try_wait.parity.shared::cta.b64 p, [%1], %2, 20000;\nadd.s32 %0, %0, -64;\n" \
               "setp.gt.and.s32 q, %0, 0, !p;\n@q bra.uni W_%=;\n}\n" : "+r"(budget) : "r"((uint32_t)(bar)), "r"((uint32_t)(parity)) : "memory")
__device__ __forceinline__ void mbar_arrive_local(uint32_t bar) {
  asm volatile("mbarrier.arrive.shared::cta.b64 _, [%0];" :: "r"(bar) : "memory");
}
__device__ __forceinline__ void tma_load_2d(uint32_t dst, const CUtensorMap* tm, uint32_t bar, int c0, int c1) {
  asm volatile("cp.async.bulk.tensor.2d.shared::cluster.global.mbarrier::complete_tx::bytes [%0], [%1, {%3, %4}], [%2];"
               :: "r"(dst), "l"(tm), "r"(bar), "r"(c0), "r"(c1) : "memory");
}
__device__ __forceinline__ void tma_load_2d_mc(uint32_t dst, const CUtensorMap* tm, uint32_t bar, int c0, int c1) {
  asm volatile("cp.async.bulk.tensor.2d.shared::cluster.global.mbarrier::complete_tx::bytes.multicast::cluster [%0], [%1, {%3, %4}], [%2], %5;"
               :: "r"(dst), "l"(tm), "r"(bar), "r"(c0), "r"(c1), "h"((uint16_t)3) : "memory");
}
__device__ __forceinline__ void tma_store_2d(const CUtensorMap* tm, uint32_t src, int c0, int c1) {
  asm volatile("cp.async.bulk.tensor.2d.global.shared::cta.bulk_group [%0, {%2, %3}], [%1];"
               :: "l"(tm), "r"(src), "r"(c0), "r"(c1) : "memory");
}
__device__ __forceinline__ void tma_load_t(uint32_t dst, const CUtensorMap* tm, uint32_t bar, int c0, int row) {
  asm volatile("cp.async.bulk.tensor.4d.shared::cluster.global.mbarrier::complete_tx::bytes [%0], [%1, {%3, %5, %5, %4}], [%2];"
               :: "r"(dst), "l"(tm), "r"(bar), "r"(c0), "r"(row >> 5), "r"(0) : "memory");
}
__device__ __forceinline__ void tma_store_t(const CUtensorMap* tm, uint32_t src, int c0, int row) {
  asm volatile("cp.async.bulk.tensor.4d.global.shared::cta.bulk_group [%0, {%2, %4, %4, %3}], [%1];"
               :: "l"(tm), "r"(src), "r"(c0), "r"(row >> 5), "r"(0) : "memory");
}
__device__ __forceinline__ void bulk_commit_wait() {
  asm volatile("cp.async.bulk.commit_group;\ncp.async.bulk.wait_group 0;" ::: "memory");
}
__device__ __forceinline__ void prefetch_tmap(const CUtensorMap* tm) {
  asm volatile("prefetch.tensormap [%0];" :: "l"(tm) : "memory");
}
__device__ __forceinline__ void fence_proxy_async_global() { asm volatile("fence.proxy.async.global;" ::: "memory"); }
__device__ __forceinline__ void fence_proxy_async_smem() { asm volatile("fence.proxy.async.shared::cta;" ::: "memory"); }
__device__ __forceinline__ unsigned ld_relaxed(const unsigned* p) {
  unsigned v;
  asm volatile("ld.relaxed.gpu.global.u32 %0, [%1];" : "=r"(v) : "l"(p) : "memory");
  return v;
}
__device__ __forceinline__ void fence_acquire() { asm volatile("fence.acquire.gpu;" ::: "memory"); }
__device__ __forceinline__ void wait_flag(const unsigned* p, unsigned target) {
  int it = 0;
  while ((int)(ld_relaxed(p) - target) < 0 && ++it < (1 << 20)) {}
  fence_acquire();
}
__device__ __forceinline__ void signal_release(unsigned* p) {
  asm volatile("red.release.gpu.global.add.u32 [%0], 1;" :: "l"(p) : "memory");
}
template <int ID, int N> __device__ __forceinline__ void bar_arrive() { asm volatile("bar.arrive %0, %1;" :: "n"(ID), "n"(N) : "memory"); }
template <int ID, int N> __device__ __forceinline__ void bar_sync() { asm volatile("bar.sync %0, %1;" :: "n"(ID), "n"(N) : "memory"); }
__device__ __forceinline__ void bar_wg(int wg) { asm volatile("bar.sync %0, 128;" :: "r"(2 + wg) : "memory"); }
__device__ __forceinline__ void cluster_sync() {
  asm volatile("barrier.cluster.arrive.relaxed.aligned;\nbarrier.cluster.wait.aligned;" ::: "memory");
}
__device__ __forceinline__ void cluster_wait() { asm volatile("barrier.cluster.wait.acquire.aligned;" ::: "memory"); }
enum { BAR_X1 = 7, BAR_WF = 8  , BAR_SKEW = 10 };

__device__ __forceinline__ void wgmma_fence() { asm volatile("wgmma.fence.sync.aligned;" ::: "memory"); }
__device__ __forceinline__ void wgmma_commit() { asm volatile("wgmma.commit_group.sync.aligned;" ::: "memory"); }
template <int N> __device__ __forceinline__ void wgmma_wait() { asm volatile("wgmma.wait_group.sync.aligned %0;" :: "n"(N) : "memory"); }

template <int scale_d, int tnsp_b = 1> __device__ __forceinline__ void wgmma_n192(float* d, uint64_t descA, uint64_t descB) {
  asm volatile("{\n.reg .pred p;\nsetp.ne.b32 p, %98, 0;\n"
               "wgmma.mma_async.sync.aligned.m64n192k16.f32.bf16.bf16 {%0,%1,%2,%3,%4,%5,%6,%7,%8,%9,%10,%11,%12,%13,%14,%15,%16,%17,%18,%19,%20,%21,%22,%23,%24,%25,%26,%27,%28,%29,%30,%31,%32,%33,%34,%35,%36,%37,%38,%39,%40,%41,%42,%43,%44,%45,%46,%47,%48,%49,%50,%51,%52,%53,%54,%55,%56,%57,%58,%59,%60,%61,%62,%63,%64,%65,%66,%67,%68,%69,%70,%71,%72,%73,%74,%75,%76,%77,%78,%79,%80,%81,%82,%83,%84,%85,%86,%87,%88,%89,%90,%91,%92,%93,%94,%95}, %96, %97, p, 1, 1, 0, %99;\n}\n"
               : "+f"(d[0]), "+f"(d[1]), "+f"(d[2]), "+f"(d[3]), "+f"(d[4]), "+f"(d[5]), "+f"(d[6]), "+f"(d[7]), "+f"(d[8]), "+f"(d[9]), "+f"(d[10]), "+f"(d[11]), "+f"(d[12]), "+f"(d[13]), "+f"(d[14]), "+f"(d[15]), "+f"(d[16]), "+f"(d[17]), "+f"(d[18]), "+f"(d[19]), "+f"(d[20]), "+f"(d[21]), "+f"(d[22]), "+f"(d[23]), "+f"(d[24]), "+f"(d[25]), "+f"(d[26]), "+f"(d[27]), "+f"(d[28]), "+f"(d[29]), "+f"(d[30]), "+f"(d[31]), "+f"(d[32]), "+f"(d[33]), "+f"(d[34]), "+f"(d[35]), "+f"(d[36]), "+f"(d[37]), "+f"(d[38]), "+f"(d[39]), "+f"(d[40]), "+f"(d[41]), "+f"(d[42]), "+f"(d[43]), "+f"(d[44]), "+f"(d[45]), "+f"(d[46]), "+f"(d[47]), "+f"(d[48]), "+f"(d[49]), "+f"(d[50]), "+f"(d[51]), "+f"(d[52]), "+f"(d[53]), "+f"(d[54]), "+f"(d[55]), "+f"(d[56]), "+f"(d[57]), "+f"(d[58]), "+f"(d[59]), "+f"(d[60]), "+f"(d[61]), "+f"(d[62]), "+f"(d[63]), "+f"(d[64]), "+f"(d[65]), "+f"(d[66]), "+f"(d[67]), "+f"(d[68]), "+f"(d[69]), "+f"(d[70]), "+f"(d[71]), "+f"(d[72]), "+f"(d[73]), "+f"(d[74]), "+f"(d[75]), "+f"(d[76]), "+f"(d[77]), "+f"(d[78]), "+f"(d[79]), "+f"(d[80]), "+f"(d[81]), "+f"(d[82]), "+f"(d[83]), "+f"(d[84]), "+f"(d[85]), "+f"(d[86]), "+f"(d[87]), "+f"(d[88]), "+f"(d[89]), "+f"(d[90]), "+f"(d[91]), "+f"(d[92]), "+f"(d[93]), "+f"(d[94]), "+f"(d[95])
               : "l"(descA), "l"(descB), "n"(scale_d), "n"(tnsp_b));
}
template <int scale_d> __device__ __forceinline__ void wgmma4_n192(float* d, uint32_t da, uint32_t db) {
#define R_ "{%0,%1,%2,%3,%4,%5,%6,%7,%8,%9,%10,%11,%12,%13,%14,%15,%16,%17,%18,%19,%20,%21,%22,%23,%24,%25,%26,%27,%28,%29,%30,%31,%32,%33,%34,%35,%36,%37,%38,%39,%40,%41,%42,%43,%44,%45,%46,%47,%48,%49,%50,%51,%52,%53,%54,%55,%56,%57,%58,%59,%60,%61,%62,%63,%64,%65,%66,%67,%68,%69,%70,%71,%72,%73,%74,%75,%76,%77,%78,%79,%80,%81,%82,%83,%84,%85,%86,%87,%88,%89,%90,%91,%92,%93,%94,%95}"
  asm volatile("{\n.reg .pred p, q;\n.reg .b64 a, b;\nsetp.ne.b32 p, %98, 0;\nsetp.eq.b32 q, 0, 0;\nmov.b64 a, {%96, 0x40000040};\nmov.b64 b, {%97, 0x40000040};\n"
               "wgmma.mma_async.sync.aligned.m64n192k16.f32.bf16.bf16 " R_ ", a, b, p, 1, 1, 0, 1;\nadd.s64 a, a, 2;\nadd.s64 b, b, 128;\n"
               "wgmma.mma_async.sync.aligned.m64n192k16.f32.bf16.bf16 " R_ ", a, b, q, 1, 1, 0, 1;\nadd.s64 a, a, 2;\nadd.s64 b, b, 128;\n"
               "wgmma.mma_async.sync.aligned.m64n192k16.f32.bf16.bf16 " R_ ", a, b, q, 1, 1, 0, 1;\nadd.s64 a, a, 2;\nadd.s64 b, b, 128;\n"
               "wgmma.mma_async.sync.aligned.m64n192k16.f32.bf16.bf16 " R_ ", a, b, q, 1, 1, 0, 1;\n}\n"
               : "+f"(d[0]), "+f"(d[1]), "+f"(d[2]), "+f"(d[3]), "+f"(d[4]), "+f"(d[5]), "+f"(d[6]), "+f"(d[7]), "+f"(d[8]), "+f"(d[9]), "+f"(d[10]), "+f"(d[11]), "+f"(d[12]), "+f"(d[13]), "+f"(d[14]), "+f"(d[15]), "+f"(d[16]), "+f"(d[17]), "+f"(d[18]), "+f"(d[19]), "+f"(d[20]), "+f"(d[21]), "+f"(d[22]), "+f"(d[23]), "+f"(d[24]), "+f"(d[25]), "+f"(d[26]), "+f"(d[27]), "+f"(d[28]), "+f"(d[29]), "+f"(d[30]), "+f"(d[31]), "+f"(d[32]), "+f"(d[33]), "+f"(d[34]), "+f"(d[35]), "+f"(d[36]), "+f"(d[37]), "+f"(d[38]), "+f"(d[39]), "+f"(d[40]), "+f"(d[41]), "+f"(d[42]), "+f"(d[43]), "+f"(d[44]), "+f"(d[45]), "+f"(d[46]), "+f"(d[47]), "+f"(d[48]), "+f"(d[49]), "+f"(d[50]), "+f"(d[51]), "+f"(d[52]), "+f"(d[53]), "+f"(d[54]), "+f"(d[55]), "+f"(d[56]), "+f"(d[57]), "+f"(d[58]), "+f"(d[59]), "+f"(d[60]), "+f"(d[61]), "+f"(d[62]), "+f"(d[63]), "+f"(d[64]), "+f"(d[65]), "+f"(d[66]), "+f"(d[67]), "+f"(d[68]), "+f"(d[69]), "+f"(d[70]), "+f"(d[71]), "+f"(d[72]), "+f"(d[73]), "+f"(d[74]), "+f"(d[75]), "+f"(d[76]), "+f"(d[77]), "+f"(d[78]), "+f"(d[79]), "+f"(d[80]), "+f"(d[81]), "+f"(d[82]), "+f"(d[83]), "+f"(d[84]), "+f"(d[85]), "+f"(d[86]), "+f"(d[87]), "+f"(d[88]), "+f"(d[89]), "+f"(d[90]), "+f"(d[91]), "+f"(d[92]), "+f"(d[93]), "+f"(d[94]), "+f"(d[95])
               : "r"(da), "r"(db), "n"(scale_d));
#undef R_
}
template <int scale_d> __device__ __forceinline__ void wgmma4_n128(float* d, uint32_t da, uint32_t db) {
#define R_ "{%0,%1,%2,%3,%4,%5,%6,%7,%8,%9,%10,%11,%12,%13,%14,%15,%16,%17,%18,%19,%20,%21,%22,%23,%24,%25,%26,%27,%28,%29,%30,%31,%32,%33,%34,%35,%36,%37,%38,%39,%40,%41,%42,%43,%44,%45,%46,%47,%48,%49,%50,%51,%52,%53,%54,%55,%56,%57,%58,%59,%60,%61,%62,%63}"
  asm volatile("{\n.reg .pred p, q;\n.reg .b64 a, b;\nsetp.ne.b32 p, %66, 0;\nsetp.eq.b32 q, 0, 0;\nmov.b64 a, {%64, 0x40000040};\nmov.b64 b, {%65, 0x40000040};\n"
               "wgmma.mma_async.sync.aligned.m64n128k16.f32.bf16.bf16 " R_ ", a, b, p, 1, 1, 0, 1;\nadd.s64 a, a, 2;\nadd.s64 b, b, 128;\n"
               "wgmma.mma_async.sync.aligned.m64n128k16.f32.bf16.bf16 " R_ ", a, b, q, 1, 1, 0, 1;\nadd.s64 a, a, 2;\nadd.s64 b, b, 128;\n"
               "wgmma.mma_async.sync.aligned.m64n128k16.f32.bf16.bf16 " R_ ", a, b, q, 1, 1, 0, 1;\nadd.s64 a, a, 2;\nadd.s64 b, b, 128;\n"
               "wgmma.mma_async.sync.aligned.m64n128k16.f32.bf16.bf16 " R_ ", a, b, q, 1, 1, 0, 1;\n}\n"
               : "+f"(d[0]), "+f"(d[1]), "+f"(d[2]), "+f"(d[3]), "+f"(d[4]), "+f"(d[5]), "+f"(d[6]), "+f"(d[7]), "+f"(d[8]), "+f"(d[9]), "+f"(d[10]), "+f"(d[11]), "+f"(d[12]), "+f"(d[13]), "+f"(d[14]), "+f"(d[15]), "+f"(d[16]), "+f"(d[17]), "+f"(d[18]), "+f"(d[19]), "+f"(d[20]), "+f"(d[21]), "+f"(d[22]), "+f"(d[23]), "+f"(d[24]), "+f"(d[25]), "+f"(d[26]), "+f"(d[27]), "+f"(d[28]), "+f"(d[29]), "+f"(d[30]), "+f"(d[31]), "+f"(d[32]), "+f"(d[33]), "+f"(d[34]), "+f"(d[35]), "+f"(d[36]), "+f"(d[37]), "+f"(d[38]), "+f"(d[39]), "+f"(d[40]), "+f"(d[41]), "+f"(d[42]), "+f"(d[43]), "+f"(d[44]), "+f"(d[45]), "+f"(d[46]), "+f"(d[47]), "+f"(d[48]), "+f"(d[49]), "+f"(d[50]), "+f"(d[51]), "+f"(d[52]), "+f"(d[53]), "+f"(d[54]), "+f"(d[55]), "+f"(d[56]), "+f"(d[57]), "+f"(d[58]), "+f"(d[59]), "+f"(d[60]), "+f"(d[61]), "+f"(d[62]), "+f"(d[63])
               : "r"(da), "r"(db), "n"(scale_d));
#undef R_
}
template <int scale_d> __device__ __forceinline__ void wgmma_n32(float* d, uint64_t descA, uint64_t descB) {
  asm volatile("{\n.reg .pred p;\nsetp.ne.b32 p, %18, 0;\n"
               "wgmma.mma_async.sync.aligned.m64n32k16.f32.bf16.bf16 {%0,%1,%2,%3,%4,%5,%6,%7,%8,%9,%10,%11,%12,%13,%14,%15}, %16, %17, p, 1, 1, 0, 1;\n}\n"
               : "+f"(d[0]), "+f"(d[1]), "+f"(d[2]), "+f"(d[3]), "+f"(d[4]), "+f"(d[5]), "+f"(d[6]), "+f"(d[7]), "+f"(d[8]), "+f"(d[9]), "+f"(d[10]), "+f"(d[11]), "+f"(d[12]), "+f"(d[13]), "+f"(d[14]), "+f"(d[15])
               : "l"(descA), "l"(descB), "n"(scale_d));
}
template <int scale_d, int tnsp_a> __device__ __forceinline__ void wgmma_n40(float* d, uint64_t descA, uint64_t descB) {
  asm volatile("{\n.reg .pred p;\nsetp.ne.b32 p, %22, 0;\n"
               "wgmma.mma_async.sync.aligned.m64n40k16.f32.bf16.bf16 {%0,%1,%2,%3,%4,%5,%6,%7,%8,%9,%10,%11,%12,%13,%14,%15,%16,%17,%18,%19}, %20, %21, p, 1, 1, %23, 1;\n}\n"
               : "+f"(d[0]), "+f"(d[1]), "+f"(d[2]), "+f"(d[3]), "+f"(d[4]), "+f"(d[5]), "+f"(d[6]), "+f"(d[7]), "+f"(d[8]), "+f"(d[9]), "+f"(d[10]), "+f"(d[11]), "+f"(d[12]), "+f"(d[13]), "+f"(d[14]), "+f"(d[15]), "+f"(d[16]), "+f"(d[17]), "+f"(d[18]), "+f"(d[19])
               : "l"(descA), "l"(descB), "n"(scale_d), "n"(tnsp_a));
}
template <int scale_d> __device__ __forceinline__ void wgmma_n40_rs(float* d, const uint32_t* a, uint64_t descB) {
  asm volatile("{\n.reg .pred p;\nsetp.ne.b32 p, %25, 0;\n"
               "wgmma.mma_async.sync.aligned.m64n40k16.f32.bf16.bf16 {%0,%1,%2,%3,%4,%5,%6,%7,%8,%9,%10,%11,%12,%13,%14,%15,%16,%17,%18,%19}, {%20,%21,%22,%23}, %24, p, 1, 1, 1;\n}\n"
               : "+f"(d[0]), "+f"(d[1]), "+f"(d[2]), "+f"(d[3]), "+f"(d[4]), "+f"(d[5]), "+f"(d[6]), "+f"(d[7]), "+f"(d[8]), "+f"(d[9]), "+f"(d[10]), "+f"(d[11]), "+f"(d[12]), "+f"(d[13]), "+f"(d[14]), "+f"(d[15]), "+f"(d[16]), "+f"(d[17]), "+f"(d[18]), "+f"(d[19])
               : "r"(a[0]), "r"(a[1]), "r"(a[2]), "r"(a[3]), "l"(descB), "n"(scale_d));
}
__device__ __forceinline__ void wgmma_copy(float* d, uint32_t da, uint64_t descB) {
  asm volatile("{\n.reg .pred p;\n.reg .b64 a;\nsetp.ne.b32 p, 0, 0;\nmov.b64 a, {%64, 0x40000040};\n"
               "wgmma.mma_async.sync.aligned.m64n16k16.f32.bf16.bf16 {%0,%1,%2,%3,%4,%5,%6,%7}, a, %65, p, 1, 1, 0, 0;\nadd.s64 a, a, 2;\n"
               "wgmma.mma_async.sync.aligned.m64n16k16.f32.bf16.bf16 {%8,%9,%10,%11,%12,%13,%14,%15}, a, %65, p, 1, 1, 0, 0;\nadd.s64 a, a, 2;\n"
               "wgmma.mma_async.sync.aligned.m64n16k16.f32.bf16.bf16 {%16,%17,%18,%19,%20,%21,%22,%23}, a, %65, p, 1, 1, 0, 0;\nadd.s64 a, a, 2;\n"
               "wgmma.mma_async.sync.aligned.m64n16k16.f32.bf16.bf16 {%24,%25,%26,%27,%28,%29,%30,%31}, a, %65, p, 1, 1, 0, 0;\nadd.s64 a, a, 1018;\n"
               "wgmma.mma_async.sync.aligned.m64n16k16.f32.bf16.bf16 {%32,%33,%34,%35,%36,%37,%38,%39}, a, %65, p, 1, 1, 0, 0;\nadd.s64 a, a, 2;\n"
               "wgmma.mma_async.sync.aligned.m64n16k16.f32.bf16.bf16 {%40,%41,%42,%43,%44,%45,%46,%47}, a, %65, p, 1, 1, 0, 0;\nadd.s64 a, a, 2;\n"
               "wgmma.mma_async.sync.aligned.m64n16k16.f32.bf16.bf16 {%48,%49,%50,%51,%52,%53,%54,%55}, a, %65, p, 1, 1, 0, 0;\nadd.s64 a, a, 2;\n"
               "wgmma.mma_async.sync.aligned.m64n16k16.f32.bf16.bf16 {%56,%57,%58,%59,%60,%61,%62,%63}, a, %65, p, 1, 1, 0, 0;\n"
               "}\n"
               : "+f"(d[0]), "+f"(d[1]), "+f"(d[2]), "+f"(d[3]), "+f"(d[4]), "+f"(d[5]), "+f"(d[6]), "+f"(d[7]), "+f"(d[8]), "+f"(d[9]), "+f"(d[10]), "+f"(d[11]), "+f"(d[12]), "+f"(d[13]), "+f"(d[14]), "+f"(d[15]), "+f"(d[16]), "+f"(d[17]), "+f"(d[18]), "+f"(d[19]), "+f"(d[20]), "+f"(d[21]), "+f"(d[22]), "+f"(d[23]), "+f"(d[24]), "+f"(d[25]), "+f"(d[26]), "+f"(d[27]), "+f"(d[28]), "+f"(d[29]), "+f"(d[30]), "+f"(d[31]), "+f"(d[32]), "+f"(d[33]), "+f"(d[34]), "+f"(d[35]), "+f"(d[36]), "+f"(d[37]), "+f"(d[38]), "+f"(d[39]), "+f"(d[40]), "+f"(d[41]), "+f"(d[42]), "+f"(d[43]), "+f"(d[44]), "+f"(d[45]), "+f"(d[46]), "+f"(d[47]), "+f"(d[48]), "+f"(d[49]), "+f"(d[50]), "+f"(d[51]), "+f"(d[52]), "+f"(d[53]), "+f"(d[54]), "+f"(d[55]), "+f"(d[56]), "+f"(d[57]), "+f"(d[58]), "+f"(d[59]), "+f"(d[60]), "+f"(d[61]), "+f"(d[62]), "+f"(d[63])
               : "r"(da), "l"(descB));
}
__device__ __forceinline__ uint64_t make_desc(uint32_t addr, uint32_t lbo_bytes, uint32_t sbo_bytes) {
  return (uint64_t)((addr & 0x3FFFF) >> 4) | ((uint64_t)(lbo_bytes >> 4) << 16) | ((uint64_t)(sbo_bytes >> 4) << 32) | (1ull << 62);
}

__device__ __forceinline__ void ldsm_x4(uint32_t addr, uint32_t& r0, uint32_t& r1, uint32_t& r2, uint32_t& r3) {
  asm volatile("ldmatrix.sync.aligned.m8n8.x4.shared.b16 {%0,%1,%2,%3}, [%4];" : "=r"(r0), "=r"(r1), "=r"(r2), "=r"(r3) : "r"(addr) : "memory");
}
__device__ __forceinline__ void ldsm_x4_t(uint32_t addr, uint32_t& r0, uint32_t& r1, uint32_t& r2, uint32_t& r3) {
  asm volatile("ldmatrix.sync.aligned.m8n8.x4.trans.shared.b16 {%0,%1,%2,%3}, [%4];" : "=r"(r0), "=r"(r1), "=r"(r2), "=r"(r3) : "r"(addr) : "memory");
}
__device__ __forceinline__ void stsm_x4(uint32_t addr, uint32_t r0, uint32_t r1, uint32_t r2, uint32_t r3) {
  asm volatile("stmatrix.sync.aligned.m8n8.x4.shared.b16 [%0], {%1,%2,%3,%4};" :: "r"(addr), "r"(r0), "r"(r1), "r"(r2), "r"(r3) : "memory");
}
__device__ __forceinline__ void stsm_x4_t(uint32_t addr, uint32_t r0, uint32_t r1, uint32_t r2, uint32_t r3) {
  asm volatile("stmatrix.sync.aligned.m8n8.x4.trans.shared.b16 [%0], {%1,%2,%3,%4};" :: "r"(addr), "r"(r0), "r"(r1), "r"(r2), "r"(r3) : "memory");
}
__device__ __forceinline__ void sts128(uint32_t addr, uint32_t a, uint32_t b, uint32_t c, uint32_t d) {
  asm volatile("st.shared.v4.u32 [%0], {%1,%2,%3,%4};" :: "r"(addr), "r"(a), "r"(b), "r"(c), "r"(d) : "memory");
}
__device__ __forceinline__ float lds32f(uint32_t addr) {
  float v;
  asm volatile("ld.shared.f32 %0, [%1];" : "=f"(v) : "r"(addr) : "memory");
  return v;
}
__device__ __forceinline__ void sts32f(uint32_t addr, float a) {
  asm volatile("st.shared.f32 [%0], %1;" :: "r"(addr), "f"(a) : "memory");
}
__device__ __forceinline__ void mma_bf16(float (&c)[4], uint32_t a0, uint32_t a1, uint32_t a2, uint32_t a3, uint32_t b0, uint32_t b1) {
  asm volatile("mma.sync.aligned.m16n8k16.row.col.f32.bf16.bf16.f32 {%0,%1,%2,%3}, {%4,%5,%6,%7}, {%8,%9}, {%0,%1,%2,%3};"
               : "+f"(c[0]), "+f"(c[1]), "+f"(c[2]), "+f"(c[3]) : "r"(a0), "r"(a1), "r"(a2), "r"(a3), "r"(b0), "r"(b1));
}
__device__ __forceinline__ void mma_bf16_z(float (&c)[4], uint32_t a0, uint32_t a1, uint32_t a2, uint32_t a3, uint32_t b0, uint32_t b1) {
  asm volatile("mma.sync.aligned.m16n8k16.row.col.f32.bf16.bf16.f32 {%0,%1,%2,%3}, {%4,%5,%6,%7}, {%8,%9}, {%10,%10,%10,%10};"
               : "=f"(c[0]), "=f"(c[1]), "=f"(c[2]), "=f"(c[3]) : "r"(a0), "r"(a1), "r"(a2), "r"(a3), "r"(b0), "r"(b1), "f"(0.f));
}
__device__ __forceinline__ uint32_t movm_t(uint32_t v) {
  uint32_t r;
  asm volatile("movmatrix.sync.aligned.m8n8.trans.b16 %0, %1;" : "=r"(r) : "r"(v));
  return r;
}
__device__ __forceinline__ uint32_t pack_bf16(float lo, float hi) {
  uint32_t r;
  asm("cvt.rn.bf16x2.f32 %0, %1, %2;" : "=r"(r) : "f"(hi), "f"(lo));
  return r;
}
__device__ __forceinline__ float bf_lo(uint32_t v) { return __uint_as_float(v << 16); }
__device__ __forceinline__ float bf_hi(uint32_t v) { return __uint_as_float(v & 0xFFFF0000u); }
__device__ __forceinline__ void split3(float x, uint32_t& h, uint32_t& m, uint32_t& l) {
  h = pack_bf16(x, 0.f); x -= bf_lo(h);
  m = pack_bf16(x, 0.f); x -= bf_lo(m);
  l = pack_bf16(x, 0.f);
}
__device__ __forceinline__ float ex2(float x) { float r; asm("ex2.approx.ftz.f32 %0, %1;" : "=f"(r) : "f"(x)); return r; }
__device__ __forceinline__ float rcp_fast(float x) { float r; asm("rcp.approx.ftz.f32 %0, %1;" : "=f"(r) : "f"(x)); return r; }
__device__ __forceinline__ void red_v4(float* p, float a, float b, float c, float d) {
  asm volatile("red.global.add.v4.f32 [%0], {%1, %2, %3, %4};" :: "l"(p), "f"(a), "f"(b), "f"(c), "f"(d) : "memory");
}
__device__ __forceinline__ uint4 ld_ll(const uint4* p) {
  uint4 v;
  asm volatile("{\n.reg .b64 a, b;\nld.relaxed.gpu.global.v2.b64 {a, b}, [%4];\nmov.b64 {%0, %1}, a;\nmov.b64 {%2, %3}, b;\n}\n"
               : "=r"(v.x), "=r"(v.y), "=r"(v.z), "=r"(v.w) : "l"(p) : "memory");
  return v;
}
__device__ __forceinline__ void st_b64(uint2* p, uint32_t a, uint32_t b) {
  asm volatile("{\n.reg .b64 v;\nmov.b64 v, {%1, %2};\nst.relaxed.gpu.global.b64 [%0], v;\n}\n" :: "l"(p), "r"(a), "r"(b) : "memory");
}
__device__ __forceinline__ void st_b128(uint4* p, uint32_t a, uint32_t b, uint32_t c, uint32_t d) {
  asm volatile("{\n.reg .b128 v;\nmov.b128 v, {%1, %2, %3, %4};\nst.relaxed.gpu.global.b128 [%0], v;\n}\n" :: "l"(p), "r"(a), "r"(b), "r"(c), "r"(d) : "memory");
}
__device__ __forceinline__ uint4 ld_b128(const uint4* p) {
  uint4 v;
  asm volatile("{\n.reg .b128 v;\nld.relaxed.gpu.global.b128 v, [%4];\nmov.b128 {%0, %1, %2, %3}, v;\n}\n" : "=r"(v.x), "=r"(v.y), "=r"(v.z), "=r"(v.w) : "l"(p) : "memory");
  return v;
}

constexpr float LOG2E = 1.4426950408889634f;

struct Params {
  const __nv_bfloat16* x0;
  const __nv_bfloat16* wA_qkv;
  const __nv_bfloat16* wA_o;
  const __nv_bfloat16* wB_qkv;
  const __nv_bfloat16* wB_phi;
  const __nv_bfloat16* wB_o;
  __nv_bfloat16* out;
};

#define ACC_DEF(d, n) _Pragma("unroll") for (int i_ = 0; i_ < (n); i_++) asm volatile("" : "=f"(d[i_]))
#define ACC_FENCE(d, n) _Pragma("unroll") for (int i_ = 0; i_ < (n); i_++) asm volatile("" : "+f"(d[i_]) :: "memory")
#define PIN(a, n) _Pragma("unroll") for (int i_ = 0; i_ < (n); i_++) asm volatile("" : "+f"((a)[i_]))
#define PINU(a, n) _Pragma("unroll") for (int i_ = 0; i_ < (n); i_++) asm volatile("" : "+r"((a)[i_]))

#define V_ADDR(p0, sw) uint32_t va_[2] = {(p0) + (srowoff >> 1) + (lhi ^ lsw2 ^ (sw)), (p0) + (srowoff >> 1) + ((32 + lhi) ^ lsw2 ^ (sw))}
#define STAGE_V(acc) { \
    _Pragma("unroll") for (int j_ = 0; j_ < 4; j_++) { \
      const float* a_ = (acc) + j_ * 8; \
      stsm_x4(va_[j_ & 1] + (j_ >> 1) * 8192, \
              pack_bf16(rs0 * a_[0], rs0 * a_[1]), pack_bf16(rs1 * a_[2], rs1 * a_[3]), pack_bf16(rs0 * a_[4], rs0 * a_[5]), pack_bf16(rs1 * a_[6], rs1 * a_[7])); } }
#define FRAG(dst, acc, TR, grp) { \
    _Pragma("unroll") for (int i_ = 15; i_ >= 0; i_--) { \
      const float r_ = (i_ & 8) ? rs1 : rs0; \
      const uint32_t w_ = pack_bf16(r_ * (acc)[4 * (i_ & 7) + (i_ >> 3) * 2], r_ * (acc)[4 * (i_ & 7) + (i_ >> 3) * 2 + 1]); \
      (dst)[8 + i_] = (TR) ? movm_t(w_) : w_; \
      if (i_ == 8 && warp >= 6 && mm < 15) { \
        _Pragma("unroll") for (int j_ = 0; j_ < 2; j_++) \
          st_b128(g_halo + (size_t)(mm * 8 + jj) * 512 + ((grp) * 4 + warp * 2 - 12 + j_) * 32 + lane, ((dst)[16 + j_ * 4] & ~1u) | H_BIT(l), (dst)[17 + j_ * 4], (dst)[18 + j_ * 4], (dst)[19 + j_ * 4]); } } \
    PINU((dst) + 8, 16); }
#define FRAG_PUT(src, slot) if (warp < 6) { _Pragma("unroll") for (int j_ = 0; j_ < 2; j_++) \
      sts128(sbase + OFF_S + (slot) * 8192 + 2048 + warp * 1024 + j_ * 512 + lane * 16, (src)[j_ * 4], (src)[j_ * 4 + 1], (src)[j_ * 4 + 2], (src)[j_ * 4 + 3]); }
#define FRAG_GET(dst, slot) { _Pragma("unroll") for (int j_ = 0; j_ < 2; j_++) \
      asm volatile("ld.shared.v4.u32 {%0, %1, %2, %3}, [%4];" : "=r"((dst)[j_ * 4]), "=r"((dst)[j_ * 4 + 1]), "=r"((dst)[j_ * 4 + 2]), "=r"((dst)[j_ * 4 + 3]) \
                   : "r"(sbase + OFF_S + (slot) * 8192 + warp * 1024 + j_ * 512 + lane * 16) : "memory"); }
#define RW(j) (((j) >> 1) * 4 + ((j) & 1))
template <int POS> __device__ __forceinline__ float exps16_(float* o, const float* p) {
  float s[4];
#pragma unroll
  for (int j = 0; j < 16; j++) { o[j] = ex2(POS ? p[RW(j)] : -p[RW(j)]); if (j < 4) s[j] = o[j]; else s[j & 3] += o[j]; }
  const float r = (s[0] + s[1]) + (s[2] + s[3]);
  return r + __shfl_xor_sync(0xffffffffu, r, 1);
}
template <int POS> __device__ __forceinline__ void exps16_fix(float* o, const float* p, float& sum) {
  if (__builtin_expect(__any_sync(0xffffffffu, !(sum > SUMLO && sum < SUMHI)), 0)) {
    float m = p[0], q[32];
#pragma unroll
    for (int j = 1; j < 16; j++) m = POS ? fmaxf(m, p[RW(j)]) : fminf(m, p[RW(j)]);
    const float x = __shfl_xor_sync(0xffffffffu, m, 1);
    m = POS ? fmaxf(m, x) : fminf(m, x);
#pragma unroll
    for (int j = 0; j < 16; j++) q[RW(j)] = p[RW(j)] - m;
    sum = exps16_<POS>(o, q);
  }
}
__device__ __forceinline__ void store16(const float* e, float sum, uint32_t dst, uint32_t dsw, int c0) {
  const float inv = rcp_fast(sum);
#pragma unroll
  for (int j = 0; j < 2; j++)
    sts128(dst + (((c0 + j) << 4) ^ dsw), pack_bf16(e[j * 8] * inv, e[j * 8 + 1] * inv), pack_bf16(e[j * 8 + 2] * inv, e[j * 8 + 3] * inv),
           pack_bf16(e[j * 8 + 4] * inv, e[j * 8 + 5] * inv), pack_bf16(e[j * 8 + 6] * inv, e[j * 8 + 7] * inv));
}
template <int POS> __device__ __forceinline__ void expp16(uint32_t* o, float* p) {
  {
#pragma unroll
    for (int r = 0; r < 4; r += 2) {
      float m = p[r];
#pragma unroll
      for (int j = 1; j < 8; j++) m = POS ? fmaxf(m, p[r + RW(j)]) : fminf(m, p[r + RW(j)]);
#pragma unroll
      for (int s = 1; s <= 2; s <<= 1) { const float x = __shfl_xor_sync(0xffffffffu, m, s); m = POS ? fmaxf(m, x) : fminf(m, x); }
#pragma unroll
      for (int j = 0; j < 8; j++) p[r + RW(j)] -= m;
    }
  }
#pragma unroll
  for (int j = 0; j < 8; j++) o[j] = pack_bf16(ex2(POS ? p[2 * j] : -p[2 * j]), ex2(POS ? p[2 * j + 1] : -p[2 * j + 1]));
}
__device__ __forceinline__ void scale32(float* o, const float* p, float c0, float c1) {
#pragma unroll
  for (int i = 0; i < 32; i++) asm volatile("mul.f32 %0, %1, %2;" : "=f"(o[i]) : "f"(p[i]), "f"((i & 2) ? c1 : c0));
}
__device__ __forceinline__ bool any_big(const float* p) {
  float m[4];
#pragma unroll
  for (int i = 0; i < 32; i++) m[i >> 3] = (i & 7) ? fmaf(p[i], p[i], m[i >> 3]) : p[i] * p[i];
  return __any_sync(0xffffffffu, !(fmaxf(fmaxf(m[0], m[1]), fmaxf(m[2], m[3])) < BIGLIM));
}
__device__ __forceinline__ void phiq_a(float* p, bool big) {
  if (__builtin_expect(!big, 1)) {
#pragma unroll
    for (int j = 0; j < 16; j++) p[j] = ex2(p[j]);
  }
}
template <int NEXT> __device__ __forceinline__ void phiq_b(uint32_t* o, float* p, bool big) {
  if (__builtin_expect(big, 0)) {
    expp16<0>(o, p); expp16<1>(o + 8, p);
  } else {
    if (NEXT) phiq_a(p + 16, false);
#pragma unroll
    for (int j = 0; j < 4; j++) {
      const float a = p[4 * j], b = p[4 * j + 1], c = p[4 * j + 2], d = p[4 * j + 3];
      const float ab = a * b, cd = c * d, r = rcp_fast(ab * cd), x = r * cd, y = r * ab;
      o[2 * j] = pack_bf16(x * b, x * a); o[2 * j + 1] = pack_bf16(y * d, y * c);
      o[8 + 2 * j] = pack_bf16(a, b); o[9 + 2 * j] = pack_bf16(c, d);
    }
  }
}
#define SCHED_FENCE() asm volatile("pmevent 0;" ::: "memory")

__global__ void __cluster_dims__(2, 1, 1) __launch_bounds__(384, 1)
mega_kernel(const __grid_constant__ CUtensorMap tm_x0, const __grid_constant__ CUtensorMap tm_xo, const __grid_constant__ CUtensorMap tm_os,
            const __grid_constant__ CUtensorMap tm_o, const __grid_constant__ CUtensorMap tm_wf,
            const __grid_constant__ CUtensorMap tm_wqA, const __grid_constant__ CUtensorMap tm_wqB,
            const __grid_constant__ CUtensorMap tm_woA, const __grid_constant__ CUtensorMap tm_woB,
            const __grid_constant__ CUtensorMap tm_phi, const Params prm) {
  extern __shared__ __align__(1024) uint8_t smem_raw[];
  const uint32_t sbase = smem_u32(smem_raw);
  const uint32_t bar_full = sbase + OFF_BAR;
  const uint32_t bar_done = bar_full + 384;
  const uint32_t bar_stat = bar_full + 768, bar_stat2 = bar_full + 776, bar_epi = bar_full + 784, bar_phi = bar_full + 936  , bar_halo = bar_full + 904  ;
  const uint32_t bar_xr = bar_full + 800, bar_lx = bar_full + 808, bar_stg = bar_full + 832;
  const uint32_t bar_chk = bar_full + 848;

  const int warp = __shfl_sync(0xffffffffu, threadIdx.x >> 5, 0), lane = threadIdx.x & 31;
  const uint32_t bar_kx = sbase + OFF_ID + 384 + warp * 8;
  uint32_t rank;
  asm volatile("mov.u32 %0, %%cluster_ctarank;" : "=r"(rank));
  const int aux = (int)blockIdx.x - NMAIN, tp = (int)(blockIdx.x >> 1) - 4;
  const int gp = tp < 0 ? 0 : (tp < 32 ? tp & 7 : 1 + (tp - 32) % 7), me = tp < 0 ? tp + 8 : (tp < 32 ? tp >> 3 : 4 + (tp - 32) / 7);
  const int jj = me, cc = gp;
  const int cta = aux >= 0 ? -1 : (cc * 8 + jj) * 2 + (int)rank;
  const int mm = cc * 2 + (int)rank;

#define LOAD_EPOCH() const unsigned epoch = ld_relaxed(&g_flags.epoch.v), ep1 = epoch + 1; (void)epoch
  int budget = 1 << 22;

  if (cta >= 0) {
    if (warp >= 8 && warp < 8 + EARLY && elect_one()) {
      const int u = warp - 8;
      const uint32_t fb = bar_full + u * 8;
      mbar_init(fb, 1);
      asm volatile("fence.mbarrier_init.release.cluster;" ::: "memory");
      fence_proxy_async_smem();
      mbar_expect_tx(fb, QST + SLOT);
      if (u) __nanosleep(STAG2);
      tma_load_t(sbase + OFF_S + u * SLOT, &tm_x0, fb, jj * 128 + u * 64, mm * 128);
#pragma unroll
      for (int i = 0; i < 6; i++) tma_load_2d(sbase + u * QST + i * 4096, &tm_wqA, fb, jj * 128 + (i >> 1) * 1024, jj * 128 + u * 64 + (i & 1) * 32);
      if (u == 0) PROFT(472);
    }
    __syncwarp();
    {
      const int tx = threadIdx.x;
      const __nv_bfloat16* pf = (tx < 128) ? prm.x0 + (size_t)(mm * 128 + tx) * D_MODEL + jj * 128
                                           : prm.wA_qkv + (size_t)(jj * 128 + (tx & 63)) * 3072 + ((tx - 128) >> 6) * 1024 + jj * 128 + rank * 64;
      if (tx < 320) asm volatile("prefetch.global.L2 [%0];" :: "l"(pf));
      else if (tx == 320) prefetch_tmap(&tm_x0);
      else if (tx == 352) prefetch_tmap(&tm_wqA);
      else if (tx == 383) asm volatile("prefetch.global.L2 [%0];" :: "l"(&g_flags.epoch.v));
    }
    if (elect_one()) {
#pragma unroll
      for (int i = 0; i < 4; i++) {
        const int u = warp * 4 + i;
        if (u >= EARLY) mbar_init(bar_full + u * 8, ((u >= 4 && u < 11) || (u > 32 && u != 40)) ? 2 : 1); mbar_init(bar_done + u * 8, 16);
      }
      mbar_init(bar_stat + warp * 16, 0x111111181182ull >> (4 * warp) & 15);
      mbar_init(bar_stat + warp * 16 + 8, 0x111111121811ull >> (4 * warp) & 15);
      mbar_init(bar_chk + 112 + (warp & 7) * 8, 1);
      mbar_init(bar_kx, 1);
      asm volatile("fence.mbarrier_init.release.cluster;" ::: "memory");
    }
    __syncwarp();
    __syncthreads();
    asm volatile("barrier.cluster.arrive.relaxed.aligned;" ::: "memory");
  }

  if (cta < 0) {
    LOAD_EPOCH();
    const uint32_t buf = sbase + warp * SLOT, bar = sbase + OFF_BAR + warp * 16;
    const uint32_t lsw = (lane & 7) << 4, lhi = (lane >> 4) << 4, lrow = (lane & 15) * 128;
    const bool el = elect_one();
    if (el) {
      mbar_init(bar, 1); mbar_init(bar + 8, 1);
      asm volatile("fence.mbarrier_init.release.cluster;" ::: "memory");
    }
#pragma unroll 1
    for (int rd = 0; rd < (NLAYERS > 1 ? 5 : 2); rd++) {
      if (rd >= 2 && warp >= 8) break;
      const int tk = rd < 2 ? aux * 12 + warp : aux * 8 + warp;
      const int half = tk & 1;
      const int blk = rd < 2 ? (tk >> 1) * 2 + rd : (4 - rd) * 16 + (tk >> 1);
      const CUtensorMap* tm = rd < 2 ? &tm_wqA : (rd == 2 ? &tm_wqB : &tm_wf);
      const int j0 = (blk & 15) >> 1;
#define AUX_LOAD(n) { const uint32_t d_ = buf + ((n) & 1) * 8192, b_ = bar + ((n) & 1) * 8; const int r_ = kslice(j0, 2 * (n) + half) * 64; \
        mbar_expect_tx(b_, 8192); tma_load_2d(d_, tm, b_, blk * 64, r_); tma_load_2d(d_ + 4096, tm, b_, blk * 64, r_ + 32); }
      if (el) {
        if (rd == 3) { wait_flag(&g_flags.wfready[j0].v, ep1 * 16); fence_proxy_async_global(); }
        AUX_LOAD(0); AUX_LOAD(1);
      }
      __syncwarp();
      float cs[8][4];
#pragma unroll
      for (int i = 0; i < 8; i++) cs[i][0] = cs[i][1] = cs[i][2] = cs[i][3] = 0.f;
#pragma unroll 1
      for (int n = 0; n < 8; n++) {
        const uint32_t tb = buf + (n & 1) * 8192 + lrow;
        mbar_wait(bar + (n & 1) * 8, (n >> 1) & 1);
#pragma unroll
        for (int i = 0; i < 16; i++) {
          uint32_t b0, b1, b2, b3;
          ldsm_x4_t(tb + (i >> 2) * 2048 + (((i & 3) * 32 + lhi) ^ lsw), b0, b1, b2, b3);
          mma_bf16(cs[2 * (i & 3)], 0x3F803F80u, 0x3F803F80u, 0x3F803F80u, 0x3F803F80u, b0, b1);
          mma_bf16(cs[2 * (i & 3) + 1], 0x3F803F80u, 0x3F803F80u, 0x3F803F80u, 0x3F803F80u, b2, b3);
        }
        __syncwarp();
        if (el && n < 6) AUX_LOAD(n + 2);
        __syncwarp();
      }
      if (lane < 4) {
#pragma unroll
        for (int i = 0; i < 8; i++) st_b64(&g_colsum[rd >= 2][blk * 32 + i * 4 + lane][half], __float_as_uint(cs[i][0]), (__float_as_uint(cs[i][1]) & ~3u) | (ep1 & 3));
      }
      __syncwarp();
    }
  } else if (warp >= 8) {
    asm volatile("setmaxnreg.dec.sync.aligned.u32 40;");
    if (warp == 8) {
      const bool el = elect_one();
      cluster_wait();
      if (el) {
#pragma unroll 1
        for (int l = 0; l < NLAYERS; l++) {
          const uint32_t par = l & 1;
          const CUtensorMap* tqk = par ? &tm_wf : &tm_wqA;
          const CUtensorMap* tv = par ? &tm_wqB : &tm_wqA;
          const CUtensorMap* two = par ? &tm_woB : &tm_woA;
          if (l == 1) { LOAD_EPOCH(); wait_flag(&g_flags.wfready[jj].v, ep1 * 16); fence_proxy_async_global(); }
#pragma unroll 1
          for (int u = l ? 0 : EARLY; u < 32; u++) {
            if (u >= 4) mbar_wait_sl(bar_done + (u - 4) * 8, par);
            else if (l) mbar_wait_sl(bar_done + (43 + u + (u >> 1)) * 8, par ^ 1);
            else mbar_wait_sl(bar_full, 0);
            const uint32_t fb = bar_full + u * 8;
            const bool res = u < 11 || (u >= 18 && u < 22);
            mbar_expect_tx(fb, res ? QST : QST + SLOT);
            const int row = kslice(jj, u < 4 ? u & 1 : (u < 18 ? u - 2 : (u < 22 ? u - 6 : u - 20))) * 64 + (int)rank * 32;
            const int ps = u < 4 ? u >> 1 : (u >= 18), col = jj * 128 + ps * 64;
            const int c0 = par ? jj * 128 + (ps ? 0 : 1024) : col;
            const uint32_t dst = sbase + (u & 3) * QST + rank * 4096;
            tma_load_2d_mc(dst, tqk, fb, c0, row);
            tma_load_2d_mc(dst + 8192, tqk, fb, c0 + (par ? 64 : 1024), row);
            tma_load_2d_mc(dst + 16384, tv, fb, col + 2048, row);
            if (l == PRL && u >= PRU && u < PRU + 4) PROFT(473 + u - PRU);
          }
#pragma unroll 1
          for (int s = 0; s < 16; s++) {
            if (s < 5) { if (s != 2 && s != 4) mbar_wait_sl(bar_done + (28 + s) * 8, par); }
            else if (s != 14) mbar_wait_sl(bar_done + (27 + s - (s == 15)) * 8, par);
            const uint32_t fb = bar_full + (32 + s) * 8;
            mbar_expect_tx(fb, SLOT);
            tma_load_2d_mc(sbase + rank * 8192 + (uint32_t)((WO_BSLOT >> (4 * s)) & 15) * SLOT, two, fb, jj * 128 + (int)rank * 64, wslice(jj, s) * 64);
            const int ts = s + 1;
            if (s >= 5 && ts < 8) {
              mbar_expect_tx(bar_chk - 8 + ts * 8, SLOT);
              tma_load_t(sbase + (uint32_t)((WO_ASLOT(par) >> (4 * ts)) & 15) * SLOT, &tm_o, bar_chk - 8 + ts * 8, wslice(jj, ts) * 64, mm * 128);
            }
          }
        }
      }
      __syncwarp();
    } else if (warp == 9) {
      const bool el = elect_one();
      LOAD_EPOCH();
#pragma unroll 1
      for (int lp = 0; lp < 4 * NLAYERS; lp++) {
        const int l = lp >> 2, ph = lp & 3;
        if (ph == 3) continue;
        const uint32_t par = l & 1;
        const unsigned* pp = reinterpret_cast<const unsigned*>(g_obuf + (ph >> 1) * 64 + (size_t)(mm * 128 + (ph ? 0 : S_LEN) + ((lane & 7) | PROWS) * 16 + (jj & 1) * 8) * D_MODEL +
                                                               (jj >> 1) * 16 + srcb(jj, lane >> 3) * 128);
        const CUtensorMap* tm = lp ? &tm_o : &tm_x0;
        const int row = mm * 128 + ((ph || !l) ? 0 : S_LEN);
        const uint32_t bit = ph ? O_BIT(l) : X_BIT(l - 1);
        const uint32_t slots = ph ? (uint32_t)(WO_ASLOT(par) >> (ph * 32 - 28)) : 0x8769876u;
        const unsigned long long fr = ph == 0 ? XPACE : ph == 1 ? (par ? FRB : 0x35351F1E1Dull) : 0x27262524232232ull;
        uint32_t no = (lp == 0 || (lp & 7) == 1) ? 0 : (ph == 1 ? NOB : (ph ? NO1 : NOX)), v0 = 0, v1 = 0;
        mbar_wait_sl(ph ? bar_done + ((uint32_t)fr & 63) * 8 : (l ? bar_done + 47 * 8 : bar_full), ph ? par : (l ? par ^ 1 : 0));
        if (el && ph) PROFT(324 + l * 16 + ph);
        __syncwarp();
        if (no && (ph == 1 ? SPD1 : (ph ? SPD2 : SPD0))) __nanosleep(ph == 1 ? SPD1 : (ph ? SPD2 : SPD0));
        if (no) { v0 = ld_relaxed(pp); __nanosleep(POLLGAP); v1 = ld_relaxed(pp); }
#pragma unroll 1
        for (int i = 0; i < (ph == 1 ? 5 : 7); i++, no >>= 8) {
#pragma unroll 1
          for (int it = 0; (no & 0xFF) && it < (1 << 18); it++) {
            no &= __ballot_sync(0xffffffffu, (v0 ^ bit) & 1) >> (8 * i);
            if (no) v0 = ld_relaxed(pp);
            if (!(no & 0xFF)) break;
            no &= __ballot_sync(0xffffffffu, (v1 ^ bit) & 1) >> (8 * i);
            if (no) v1 = ld_relaxed(pp);
          }
          if (ph || i >= XP0) mbar_wait_sl(bar_done + ((uint32_t)(fr >> (8 * i)) & 63) * 8, par);
          if (el) {
            if (i == 0) PROFT(320 + l * 16 + ph);
            const uint32_t cb = (lp ? bar_chk + (ph >> 1) * 112 : bar_full + 32) + i * 8;
            mbar_expect_tx(cb, SLOT);
            tma_load_t(sbase + ((slots >> (4 * i)) & 15) * SLOT, tm, cb, srcb(jj, i) * 128 + (ph >> 1) * 64, row);
          }
          __syncwarp();
        }
        if (ph == 0 && el) {
          if (l) { wait_flag(&g_flags.xready[l][mm].v, ep1 * 8); fence_proxy_async_global(); }
#pragma unroll 1
          for (int u = 11; u < 34; u++) {
            if (u == 18) u = 22;
            mbar_wait_sl(bar_done + (u - 4) * 8, par);
            if (u == 32) mbar_expect_tx(bar_xr, 2 * SLOT);
            tma_load_t(sbase + OFF_RA + (u & 3) * SLOT, tm, u < 32 ? bar_full + u * 8 : bar_xr, kslice(jj, u < 18 ? u - 2 : (u < 32 ? u - 20 : u - 32)) * 64, row);
          }
        }
        __syncwarp();
      }
      if (el && atomicAdd(&g_flags.done.v, 1) == ep1 * NMAIN - 1) asm volatile("st.relaxed.gpu.global.u32 [%0], %1;" :: "l"(&g_flags.epoch.v), "r"(ep1) : "memory");
      __syncwarp();
      cluster_wait();
    } else {
      const int hw = warp - 10;
      LOAD_EPOCH();
      const bool el = elect_one();
      cluster_wait();
      if (hw == 0) {
        mbar_wait_sl(bar_full + 8, 0);
        if (lane < 7) prefetch_tmap(lane == 0 ? &tm_os : lane == 1 ? &tm_o : lane == 2 ? &tm_wf : lane == 3 ? &tm_wqB : lane == 4 ? &tm_woA : lane == 5 ? &tm_woB : &tm_phi);
#pragma unroll 1
        for (int i = 0; i < (NLAYERS > 1 ? 9 : 0); i++) {
          if (i == 0 || i == 5) mbar_wait_sl(bar_done + (i ? FD1 : FD0) * 8, 0);
          if (el) {
            if (i == 0) { mbar_expect_tx(bar_phi, 2 * SLOT + 8192); tma_load_2d(sbase + OFF_PHI, &tm_phi, bar_phi, 0, jj * 128); }
            else tma_load_2d(sbase + (i > 4 ? 10 : 12) * SLOT - 4096 + i * 4096, &tm_wqB, bar_phi, (i > 4 ? 896 : 0) + jj * 128 + ((i - 1) >> 1) * 64, mm * 64 + (~i & 1) * 32);
          }
          __syncwarp();
          __nanosleep(PFGAP);
        }
      } else {
        if (lane < 24) {
          const uint32_t one = (lane & 8) ? 0u : 0x3F80u << ((lane & 1) * 16), w = (lane >> 1) & 3;
          sts128(sbase + OFF_ID + lane * 16, w == 0 ? one : 0u, w == 1 ? one : 0u, w == 2 ? one : 0u, w == 3 ? one : 0u);
        }
#pragma unroll 1
        for (int b = 0; b < 2; b++) {
          float4* z = reinterpret_cast<float4*>(g_kv[b] + (jj * 4) * KVH + mm * (4 * KVH / 16)) + lane;
#pragma unroll
          for (int i = 0; i < 6; i++) z[i * 32] = make_float4(0.f, 0.f, 0.f, 0.f);
        }
#pragma unroll 1
        for (int i = 0; i < 16; i++) {
          const int b = i >> 2;
          const uint32_t v = (b == 0 ? O_BIT(0) : b == 1 ? X_BIT(0) : H_BIT(0)) + 1;
          uint4* p = b < 2 ? reinterpret_cast<uint4*>(g_obuf + (size_t)(b * S_LEN + mm * 128 + (i & 3) * 32 + (lane >> 3) * 8) * D_MODEL + jj * 128 + (b ? 0 : 64)) + (lane & 7)
                           : g_halo + (size_t)(mm * 8 + jj) * 512 + i * 32 + lane;
          *p = make_uint4(v, v, v, v);
        }
        fence_proxy_async_global();
      }
      __syncwarp();
      uint32_t chkp = 0;
#pragma unroll 1
      for (int lp = hw; lp < 8 * NLAYERS; lp++) {
        const int l = lp >> 3, tk = lp & 7, ph = tk ? 2 - hw : 0;
        const uint32_t par = l & 1;
        int lane; asm volatile("mov.u32 %0, %%laneid;" : "=r"(lane));
        if (tk == 5 || (hw && tk == 0)) {
          const uint32_t bit = ph ? O_BIT(l) : X_BIT(l - 1);
          uint32_t slots = ph ? (uint32_t)(WO_ASLOT(par) >> (ph * 32 - 28)) : 0x8769876u;
          const uint32_t a0 = sbase + (lane & 7) * 126 + lane * 4 + (lane & 1) * 14;
#pragma unroll 1
          for (int c = 0; c < 7; c++, slots >>= 4) {
            const uint32_t cb = bar_chk + 112 - hw * 112 + c * 8;
#pragma unroll 1
            for (int it = 0; it < (1 << 12); it++) {
              mbar_wait_sl(cb, (chkp >> c) & 1);
              chkp ^= 1u << c;
              if (el && c == 0) PROFT(ph == 1 ? 480 + l * 2 : 488 + l * 2 + (ph >> 1));
              uint32_t bad;
              asm volatile("{\n.reg .b32 w<16>;\n"
                           "ld.shared.u32 w0, [%1 + 0];\n"
                           "ld.shared.u32 w1, [%1 + 1024];\n"
                           "ld.shared.u32 w2, [%1 + 2048];\n"
                           "ld.shared.u32 w3, [%1 + 3072];\n"
                           "ld.shared.u32 w4, [%1 + 4096];\n"
                           "ld.shared.u32 w5, [%1 + 5120];\n"
                           "ld.shared.u32 w6, [%1 + 6144];\n"
                           "ld.shared.u32 w7, [%1 + 7168];\n"
                           "ld.shared.u32 w8, [%1 + 8192];\n"
                           "ld.shared.u32 w9, [%1 + 9216];\n"
                           "ld.shared.u32 w10, [%1 + 10240];\n"
                           "ld.shared.u32 w11, [%1 + 11264];\n"
                           "ld.shared.u32 w12, [%1 + 12288];\n"
                           "ld.shared.u32 w13, [%1 + 13312];\n"
                           "ld.shared.u32 w14, [%1 + 14336];\n"
                           "ld.shared.u32 w15, [%1 + 15360];\n"
                           "lop3.b32 w0, w0, w1, %2, 0x7E;\n"
                           "lop3.b32 w2, w2, w3, %2, 0x7E;\n"
                           "lop3.b32 w4, w4, w5, %2, 0x7E;\n"
                           "lop3.b32 w6, w6, w7, %2, 0x7E;\n"
                           "lop3.b32 w8, w8, w9, %2, 0x7E;\n"
                           "lop3.b32 w10, w10, w11, %2, 0x7E;\n"
                           "lop3.b32 w12, w12, w13, %2, 0x7E;\n"
                           "lop3.b32 w14, w14, w15, %2, 0x7E;\n"
                           "lop3.b32 w0, w0, w2, w4, 0xFE;\nlop3.b32 w6, w6, w8, w10, 0xFE;\nlop3.b32 w0, w0, w12, w14, 0xFE;\nlop3.b32 %0, w0, w6, 1, 0xA8;\n}\n"
                           : "=r"(bad) : "r"(a0 + (slots & 15) * SLOT), "r"(bit) : "memory");
              if (__all_sync(0xffffffffu, bad == 0)) break;
              if (el) {
                fence_proxy_async_smem();
                mbar_expect_tx(cb, SLOT);
                tma_load_t(sbase + (slots & 15) * SLOT, &tm_o, cb, srcb(jj, c) * 128 + (ph >> 1) * 64, mm * 128 + (ph ? 0 : S_LEN));
                RETRY_COUNT();
              }
              __syncwarp();
            }
            if (el) { mbar_arrive_local(bar_full + (c + (ph ? 25 + ph * 8 : 4)) * 8); if (lp == PRL * 8 && c == 0) PROFT(477); }
            __syncwarp();
          }
        } else if (hw && (tk & 5) == 1) {
          {
            const int hp = tk >> 1;
            const uint4* src = reinterpret_cast<const uint4*>(g_colsum[par][jj * 64 + hp * 32 + lane]);
            uint32_t bad;
            int it = 0;
            float c[6];
            do {
              bad = 0;
#pragma unroll
              for (int p = 0; p < 3; p++) {
                const uint4 v = ld_ll(src + ((par && p < 2) ? (hp ? -32 : 512) + p * 32 : p * 512));
                bad |= (v.y ^ ep1) | (v.w ^ ep1);
                c[2 * p] = __uint_as_float(v.x) + __uint_as_float(v.z); c[2 * p + 1] = __uint_as_float(v.y) + __uint_as_float(v.w);
              }
              bad &= 3;
              if (bad) __nanosleep(300);
            } while (bad && ++it < (1 << 16));
#pragma unroll
            for (int p = 0; p < 6; p++) {
              uint32_t h, m, lo;
              split3(c[p], h, m, lo);
              sts128(sbase + OFF_LNB + hp * 4096 + (p >> 1) * 1024 + lane * 32 + (p & 1) * 16, h | (m << 16), h | (lo << 16), h | (m << 16), lo | (m << 16));
            }
            fence_proxy_async_smem();
            __syncwarp();
            if (el) { mbar_arrive_local(hp ? bar_stat2 : bar_stat); if (hp == 0) PROFT(324 + l * 16); }
            __syncwarp();
          }
        } else if (tk == 0) {
          mbar_wait_sl(bar_done + 24, par);
          const uint4* sp = reinterpret_cast<const uint4*>(g_stats + (size_t)(mm * 128) * 8) + lane;
#pragma unroll 1
          for (int hf = 0; hf < 4; hf++) {
            uint4 v[4];
            uint32_t bad;
            int it = 0;
            do {
              bad = 0;
#pragma unroll
              for (int i = 0; i < 4; i++) { v[i] = ld_ll(sp + (hf * 4 + i) * 32); bad |= (v[i].y ^ STAT_TAG(l)) | (v[i].w ^ STAT_TAG(l)); }
              bad &= 3;
              if (bad) __nanosleep(200);
            } while (bad && ++it < (1 << 16));
            __syncwarp();
            float mean = 0.f, m2 = 0.f;
#pragma unroll
            for (int i = 0; i < 4; i++) {
              float a = __uint_as_float(v[i].x) + __uint_as_float(v[i].z);
              a += __shfl_xor_sync(0xffffffffu, a, 1); a += __shfl_xor_sync(0xffffffffu, a, 2);
              a *= 0.125f;
              const float e0 = __uint_as_float(v[i].x) - a, e1 = __uint_as_float(v[i].z) - a;
              float q = fmaf(fmaf(e0, e0, e1 * e1), 128.f, __uint_as_float(v[i].y) + __uint_as_float(v[i].w));
              q += __shfl_xor_sync(0xffffffffu, q, 1); q += __shfl_xor_sync(0xffffffffu, q, 2);
              if ((lane & 3) == i) { mean = a; m2 = q; }
            }
            const uint32_t row = hf * 32 + (lane & 3) * 8 + (lane >> 2);
            uint32_t h, m, lo;
            split3(-0.5f * mean, h, m, lo);
            sts128(sbase + OFF_LNA + row * 16, h | (h << 16), m | (h << 16), lo | (m << 16), m | (lo << 16));
            sts32f(sbase + OFF_ST + row * 4, rsqrtf(m2 * (1.f / 1024.f) + 1e-5f));
          }
          fence_proxy_async_smem();
          __syncwarp();
          if (el) { mbar_arrive_local(bar_stat); PROFT(323 + l * 16); }
          __syncwarp();
#pragma unroll 1
          for (int i = 0; i < 8 - 4 * l; i++) {
            asm volatile("prefetch.global.L2 [%0];" :: "l"(i < 4 ? (l ? prm.wB_o : prm.wA_o) + (size_t)cta * 8192 + i * 2048 + lane * 64
                                                                 : prm.wB_qkv + (size_t)(cta * 8 + (i - 4) * 2 + (lane >> 4)) * 3072 + 2048 + (lane & 15) * 64));
            __nanosleep(PFGAP);
          }
        } else if (lp == 3) {
#pragma unroll 1
          for (int c = 0; c < (NLAYERS > 1 ? 8 : 0); c++) {
            if (!(c & 3)) asm volatile("bar.sync %0, 288;" :: "r"(BAR_WF + (c >> 2)) : "memory");
            if (el) {
              tma_store_2d(&tm_wf, sbase + 11 * SLOT + c * 4096, (c < 4 ? 1024 : -128) + jj * 128 + (c >> 1) * 64, mm * 64 + (c & 1) * 32);
              if (c == 7) {
                asm volatile("cp.async.bulk.commit_group;\ncp.async.bulk.wait_group.read 0;" ::: "memory");
                mbar_arrive_local(bar_phi + 8);
              } else __nanosleep(WFGAP);
            }
            __syncwarp();
          }
          if (el) { bulk_commit_wait(); signal_release(&g_flags.wfready[jj].v); PROFT(335); }
          __syncwarp();
        } else if (tk == 2 || tk == 4) {
          if (par) continue;
          const int i = tk >> 2;
          mbar_wait_sl(bar_done + (i ? HW1 : (hw ? 19 : HW0)) * 8, 0);
          const uint4* src = g_halo + (size_t)(mm * 8 + jj - 8) * 512 + i * 256 + hw * 128 + lane;
          uint4 v[4];
          int it = 0;
          bool ok;
          do {
#pragma unroll
            for (int j = 0; j < 4; j++) v[j] = mm ? ld_b128(src + j * 32) : make_uint4(H_BIT(l), 0, 0, 0);
            ok = __all_sync(0xffffffffu, (((v[0].x ^ H_BIT(l)) | (v[1].x ^ H_BIT(l)) | (v[2].x ^ H_BIT(l)) | (v[3].x ^ H_BIT(l))) & 1) == 0);
          } while (!ok && ++it < (1 << 16));
#pragma unroll
          for (int j = 0; j < 4; j++) sts128(sbase + OFF_S + hw * 8192 + j * 512 + lane * 16, v[j].x, v[j].y, v[j].z, v[j].w);
          __syncwarp();
          if (el) { mbar_arrive_local(bar_halo + hw * 8); PROFT(331 + l * 16 + i * 2 + hw); }
          __syncwarp();
        } else if (tk == 6 && hw == 0 && l < NLAYERS - 1) {
          bar_sync<BAR_X1, 288>();
          if (el) {
            PROFT(328 + l * 16);
            mbar_wait_sl(bar_full + XD * 8, par ^ 1);
            tma_store_t(&tm_o, sbase + 11 * SLOT, jj * 128 + 64, mm * 128 + S_LEN);
            bulk_commit_wait();
            signal_release(&g_flags.xready[l + 1][mm].v);
            PROFT(330 + l * 16);
          }
          __syncwarp();
        }
      }
    }
    cluster_sync();
  } else {
    asm volatile("setmaxnreg.inc.sync.aligned.u32 232;");
    const int wg = warp >> 2;
    const int r0 = warp * 16;
    const uint32_t pK = sbase + OFF_S, pV = sbase + OFF_S + SLOT;
#define PMASKS(on, bit) const uint32_t pm0 = ((on) && t == (g >> 1)), pbit = (bit)
#define PBIT(w) (((w) & ~pm0) | (pbit & pm0))
#define LANE_CONSTS() \
    int lane; asm volatile("mov.u32 %0, %%laneid;" : "=r"(lane)); \
    const int g = lane >> 2, t = lane & 3; \
    const uint32_t srowoff = (r0 + (lane & 15)) * 128, lsw = (lane & 7) << 4, lhi = (lane >> 4) << 4, lsw2 = (lane & 6) << 3; \
    (void)g; (void)t; (void)srowoff; (void)lsw; (void)lhi; (void)lsw2;
    uint32_t stgp = 0, peer;
    asm volatile("mapa.shared::cluster.u32 %0, %1, %2;" : "=r"(peer) : "r"(sbase), "r"(rank ^ 1));
    peer -= sbase;
    const uint32_t dA0 = (((sbase & 0x3FFFF) + wg * 8192) >> 4) | 0x10000u, dB0 = ((sbase & 0x3FFFF) >> 4) | 0x2000000u;
    cluster_wait();
#define DESC(lo, hi) ((uint64_t)(uint32_t)(lo) | ((uint64_t)(hi) << 32))
#define STG_ARRIVE() { __syncwarp(); if (elect_one()) mbar_arrive_local(bar_stg); }
#define STG_WAIT() { mbar_wait(bar_stg, stgp); stgp ^= 1; }
#define PROFS() do {} while (0)
#define REL(addr) { if (elect_one()) { mbar_arrive_local(addr); asm volatile("mbarrier.arrive.shared::cluster.b64 _, [%0];" :: "r"((addr) + peer) : "memory"); } }
#define QSTEP(ACC, DA, SC) { \
      const uint32_t da = (DA), db = dB0 + (ub & 0x18) * (QST >> 7); \
      mbar_wait(ub, par); \
      wgmma_fence(); \
      wgmma4_n192<SC>(ACC, da, db); \
      wgmma_commit(); PROFS(); }
#define QREL() { wgmma_wait<1>(); REL(ub + 376); ub += 8; }
#define RA_CUR (dA0 + (OFF_RA >> 4) + (ub & 0x18) * (SLOT >> 7))
#define PUMP1() { QSTEP(S1, RA_CUR, 1); QREL(); }
#define PUMPN() { wgmma_fence(); wgmma4_n192<1>(S1, RA_CUR, dB0 + (ub & 0x18) * (QST >> 7)); wgmma_commit(); PROFS(); QREL(); }
#define PUMP0() { PUMP1(); SCHED_FENCE(); }
#define WSTEP() { \
      const uint32_t s4 = (ub - bar_full - 256) >> 1; \
      const uint32_t da = dA0 + (((uint32_t)(WO_ASLOT(par) >> s4) & 15) << 10), db = dB0 + (((uint32_t)(WO_BSLOT >> s4) & 15) << 10); \
      mbar_wait(ub, par); \
      wgmma_fence(); \
      wgmma4_n128<1>(S1, da, db); \
      wgmma_commit(); PROFS(); \
      wgmma_wait<1>(); \
      if (s4) REL(ub + 376); \
      ub += 8; }
#define PUMPS(n) { _Pragma("unroll 1") for (int i_ = 0; i_ < (n); i_++) PUMP1(); }
#define LNSTEP(ACC, hh) { wgmma_fence(); wgmma_n192<1, 0>(ACC, make_desc(sbase + OFF_LNA + wg * 1024, 0, 128) ^ (1ull << 62), make_desc(sbase + OFF_LNB + (hh) * 4096, 0, 128) ^ (1ull << 62)); }
#define WARP_STORE(tm, tile, col, row) { fence_proxy_async_smem(); __syncwarp(); \
      if (elect_one()) { tma_store_2d(tm, (tile) + r0 * 128, col, (row) + r0); asm volatile("cp.async.bulk.commit_group;" ::: "memory"); } __syncwarp(); }
#define TILE_CONSTS(base, on, bit) \
      uint32_t ta[5]; \
      { PMASKS(on, bit); (void)pbit; ta[4] = pm0; } \
      _Pragma("unroll") for (int j = 0; j < 4; j++) ta[j] = (base) + srowoff + ((((uint32_t)j << 5) + lhi) ^ lsw); \
      PINU(ta, 5); SCHED_FENCE(); \
      const uint32_t pm0 = ta[4], pbit = (bit)
#define X_OUT(pc, W) { \
      _Pragma("unroll") for (int j = 0; j < 4; j++) \
        stsm_x4(ta[j] + (pc) * SLOT, \
                PBIT(pack_bf16((W)[j * 8 + 0], (W)[j * 8 + 1])), PBIT(pack_bf16((W)[j * 8 + 2], (W)[j * 8 + 3])), \
                (pack_bf16((W)[j * 8 + 4], (W)[j * 8 + 5])), (pack_bf16((W)[j * 8 + 6], (W)[j * 8 + 7]))); }
#define REST_P1(SKEW) { \
      mbar_wait(bar_stat2, par); \
      LNSTEP(S1, 1); \
      wgmma_commit(); \
      _Pragma("unroll 1") while (ub < bar_full + 256) { \
        const bool hold = ub == bar_full + 256 - 8 * (SKEW) && wg == 0; \
        if (hold) { wgmma_wait<0>(); REL(ub + 376); bar_sync<BAR_SKEW, 256>(); } \
        QSTEP(S1, RA_CUR, 1); \
        if (ub == bar_full + 248 && wg == 1) bar_arrive<BAR_SKEW, 256>(); \
        wgmma_wait<1>(); if (!hold) REL(ub + 376); ub += 8; \
      } \
      mbar_wait(bar_done + (31 - (SKEW)) * 8, par);        \
      wgmma_wait<0>(); \
      ACC_FENCE(S1, 96); \
      REL(bar_done + 31 * 8); \
      PROF(13); }
#define FOLD(tile, rd) { \
          LANE_CONSTS(); \
          float d[32]; \
          ACC_DEF(d, 32); \
          mbar_wait(bar_phi, 0); \
          wgmma_fence(); \
          _Pragma("unroll") for (int i = 0; i < 2; i++) { \
            const uint64_t da = make_desc((tile) + wg * 8192 + i * 64, 16, 1024); \
            const uint64_t db = make_desc(sbase + OFF_PHI + wg * 4096 + i * 2048, 16, 512) ^ (3ull << 62); \
            wgmma_n32<0>(d + i * 16, da, db); wgmma_n32<1>(d + i * 16, da + 2, db + 64); \
          } \
          wgmma_commit(); \
          PUMP0(); \
          ACC_FENCE(d, 32); \
          bar_wg(wg); \
          _Pragma("unroll") for (int i = 0; i < 4; i++) { \
            const float* x = d + (i & 1) * 8 + (i >> 1) * 2; \
            if (rd) sts128((tile) + wg * 8192 + ((warp & 3) * 16 + (i >> 1) * 8 + g) * 128 + (((2 * t + (i & 1)) ^ g) << 4), \
                           pack_bf16(x[0], x[1]), pack_bf16(x[4], x[5]), pack_bf16(x[16], x[17]), pack_bf16(x[20], x[21])); \
            else stsm_x4((tile) + srowoff + ((((uint32_t)i << 5) + lhi) ^ lsw), pack_bf16(d[i * 8], d[i * 8 + 1]), pack_bf16(d[i * 8 + 2], d[i * 8 + 3]), \
                         pack_bf16(d[i * 8 + 4], d[i * 8 + 5]), pack_bf16(d[i * 8 + 6], d[i * 8 + 7])); \
          } \
          }
#define XM_ISSUE() { mbar_wait(bar_xr, par); wgmma_fence(); \
      wgmma_copy(T_, dA0 + (OFF_RA >> 4), make_desc(sbase + OFF_ID, 128, 128) ^ (1ull << 62)); }
#define COPYN(d, s, n) _Pragma("unroll") for (int i_ = 0; i_ < (n); i_++) { uint32_t c_; asm volatile("mov.b32 %0, %1;" : "=r"(c_) : "f"((s)[i_])); (d)[i_] = __uint_as_float(c_); }
#define COPY64(d, s) COPYN(d, s, 64)
#define XM_DONE() { ACC_FENCE(T_, 64); COPY64(S1, T_); ACC_FENCE(S1, 64); \
      __syncwarp(); if (elect_one()) mbar_arrive_local(bar_lx); }
#define LOAD_X() { float T_[64]; ACC_DEF(T_, 64); wgmma_wait<0>(); XM_ISSUE(); wgmma_commit(); wgmma_wait<0>(); XM_DONE(); }

    float S0[96], S1[96];
#define FIRST_STEP(l_) { const int ln_ = (l_), l = ln_; const uint32_t ub = bar_full; (void)l; (void)ub; ACC_DEF(S0, 96); wgmma_fence(); wgmma4_n192<0>(S0, dA0 + (OFF_S >> 4), dB0); wgmma_commit(); PROFS(); }
    LOAD_EPOCH();
    mbar_wait(bar_full, 0);
    FIRST_STEP(0);
#pragma unroll 1
    for (int l = 0;; l++) {
      const uint32_t par = l & 1;
      uint32_t ub = bar_full + 8;
      PROF(1);
      {
        LANE_CONSTS();
        uint32_t ta[4];
#pragma unroll
        for (int j = 0; j < 4; j++) ta[j] = pK + srowoff + ((((uint32_t)j << 5) + lhi) ^ lsw);
        float p0, p1, a0 = 0.f, a1 = 0.f, q0 = 0.f, q1 = 0.f;
#define STATS(j0, j1) _Pragma("unroll") for (int j = (j0); j < (j1); j++) { \
          uint32_t x[4]; \
          ldsm_x4(ta[j & 3] + (j >> 2) * SLOT, x[0], x[1], x[2], x[3]); \
          if (j == 0) { p0 = __shfl_sync(0xffffffffu, bf_lo(x[0]), lane & 28); p1 = __shfl_sync(0xffffffffu, bf_lo(x[1]), lane & 28); } \
          _Pragma("unroll") for (int i = 0; i < 4; i += 2) { \
            const float d0 = bf_lo(x[i]) - p0, d1 = bf_hi(x[i]) - p0, d2 = bf_lo(x[i + 1]) - p1, d3 = bf_hi(x[i + 1]) - p1; \
            a0 += d0 + d1; a1 += d2 + d3; \
            q0 = fmaf(d1, d1, fmaf(d0, d0, q0)); q1 = fmaf(d3, d3, fmaf(d2, d2, q1)); } } \
          asm volatile("" : "+f"(a0), "+f"(a1), "+f"(q0), "+f"(q1), "+f"(p0), "+f"(p1)); SCHED_FENCE()
        if (SB0) { STATS(0, SB0); }
        bar_wg(wg);
        QSTEP(S0, dA0 + ((OFF_S + SLOT) >> 4), 1);
        QREL();
        SCHED_FENCE();
        STATS(SB0, SB1);
        ACC_DEF(S1, 96);
        QSTEP(S1, dA0 + (OFF_S >> 4), 0);
        QREL();
        SCHED_FENCE();
        STATS(SB1, SB2);
        QSTEP(S1, dA0 + ((OFF_S + SLOT) >> 4), 1);
        QREL();
        SCHED_FENCE();
        STATS(SB2, 8);
#pragma unroll
        for (int o = 1; o <= 2; o <<= 1) {
          a0 += __shfl_xor_sync(0xffffffffu, a0, o); a1 += __shfl_xor_sync(0xffffffffu, a1, o);
          q0 += __shfl_xor_sync(0xffffffffu, q0, o); q1 += __shfl_xor_sync(0xffffffffu, q1, o);
        }
        if (t == 1) { a0 = a1; q0 = q1; p0 = p1; }
        if (t < 2) st_b64(g_stats + (size_t)(mm * 128 + r0 + g + t * 8) * 8 + jj, __float_as_uint(fmaf(a0, 1.f / 128.f, p0)),
                          (__float_as_uint(fmaxf(fmaf(a0 * (-1.f / 128.f), a0, q0), 0.f)) & ~3u) | STAT_TAG(l));
        if (l) { asm volatile("cp.async.bulk.wait_group 0;" ::: "memory"); bar_arrive<BAR_X1, 288>(); }
#pragma unroll 1
        for (int i = 0; i < 14; i++) {
          QSTEP(S0, RA_CUR, 1);
          if (i == 0) PROF(2);
          QREL();
        }
      }
      LANE_CONSTS();
      mbar_wait(bar_stat, par);
      LNSTEP(S0, 0);
      wgmma_commit();
      const float rs0 = lds32f(sbase + OFF_ST + (r0 + g) * 4), rs1 = lds32f(sbase + OFF_ST + (r0 + g + 8) * 4);
      PUMP0();
      ACC_FENCE(S0, 96);
      PROF(3);
      if (!par) {
        constexpr uint32_t par = 0;
        uint32_t qa[16];
        uint32_t kf[24], vf[24];
#define DRAIN_A(ACC, hp, PMP) { \
          LANE_CONSTS(); \
          FRAG(kf, ACC + 32, 0, (hp) * 2); \
          PMP; \
          FRAG(vf, ACC + 64, 1, (hp) * 2 + 1); \
          _Pragma("unroll") for (int i_ = 0; i_ < 16; i_++) qa[i_] = pack_bf16(ACC[2 * i_], ACC[2 * i_ + 1]); \
          PINU(qa, 16); }
        DRAIN_A(S0, 0, PUMP0());
        if (l == 0 && NLAYERS > 1) {
#pragma unroll 1
          for (int rd = 1; rd >= 0; rd--) {
            FOLD(sbase + (12 - rd) * SLOT, rd);
            fence_proxy_async_smem();
            asm volatile("bar.arrive %0, 288;" :: "r"(BAR_WF + 1 - rd) : "memory");
          }
        }
        PUMPS(FPUMP);
#pragma unroll 1
        for (int h = 0; h < 2; h++) {
          PROFH(4, 16);
          LANE_CONSTS();
          FRAG_PUT(kf + 16, 0); FRAG_PUT(vf + 16, 1);
          STG_ARRIVE();
          if (h) { PROF(8); LOAD_X(); PROF(9); WSTEP(); PROF(10); } else PUMPS(HPUMP2);
          const bool gt0 = 2 * t > g, gt1 = 2 * t >= g;
          uint32_t msk[2] = {(gt0 ? 0xFFFFu : 0u) | (gt1 ? 0xFFFF0000u : 0u), g == 2 * t ? 0x10001u : 0u};
          PINU(msk, 2);
          TILE_CONSTS(sbase, false, 0);
          (void)pm0; (void)pbit;
          if (h) PROF(12);
          STG_WAIT();
          if (h) PROF(14);
          if (warp < 2) mbar_wait(bar_halo, h);
          if (h) PROF(15);
          if (h == 0) mbar_wait(ub, par);
          FRAG_GET(kf, 0);
          PROFH(5, 17);
          float s[2][3][4];
#pragma unroll
          for (int ks = 0; ks < 2; ks++)
#pragma unroll
            for (int i = 0; i < 6; i++) {
              const int hh = i & 1, jb = 2 - (i >> 1);
              const uint32_t* b = kf + jb * 8 + hh * 4 + ks * 2;
              if (ks) mma_bf16(s[hh][jb], qa[hh * 8 + 4], qa[hh * 8 + 5], qa[hh * 8 + 6], qa[hh * 8 + 7], b[0], b[1]);
              else mma_bf16_z(s[hh][jb], qa[hh * 8], qa[hh * 8 + 1], qa[hh * 8 + 2], qa[hh * 8 + 3], b[0], b[1]);
            }
          if (h == 0) PUMPN()
          PROFH(6, 18);
          float va[2][2], vb[2][2], mx[2][2];
#pragma unroll
          for (int hh = 0; hh < 2; hh++) {
            va[hh][0] = gt0 ? s[hh][0][0] : s[hh][1][0];
            vb[hh][0] = gt1 ? s[hh][0][1] : s[hh][1][1];
            va[hh][1] = gt0 ? s[hh][1][2] : s[hh][2][2];
            vb[hh][1] = gt1 ? s[hh][1][3] : s[hh][2][3];
          }
          if (warp < 2 && mm == 0) {
#pragma unroll
            for (int hh = 0; hh < 2; hh++) { if (gt0) va[hh][0] = -INFINITY; if (gt1) vb[hh][0] = -INFINITY; }
          }
#pragma unroll
          for (int i = 0; i < 4; i++) mx[i >> 1][i & 1] = fmaxf(va[i >> 1][i & 1], vb[i >> 1][i & 1]);
#pragma unroll
          for (int o = 1; o <= 2; o <<= 1)
#pragma unroll
            for (int i = 0; i < 4; i++) mx[i >> 1][i & 1] = fmaxf(mx[i >> 1][i & 1], __shfl_xor_sync(0xffffffffu, mx[i >> 1][i & 1], o));
          const float sc0 = rs0 * (0.17677669529663687f * LOG2E), sc1 = rs1 * (0.17677669529663687f * LOG2E);
#pragma unroll
          for (int i = 0; i < 4; i++) {
            const float sc = (i & 1) ? sc1 : sc0, m = mx[i >> 1][i & 1];
            va[i >> 1][i & 1] = ex2((va[i >> 1][i & 1] - m) * sc); vb[i >> 1][i & 1] = ex2((vb[i >> 1][i & 1] - m) * sc);
            mx[i >> 1][i & 1] = va[i >> 1][i & 1] + vb[i >> 1][i & 1];
          }
          if (h == 0) { PIN(&va[0][0], 4); PIN(&vb[0][0], 4); PIN(&mx[0][0], 4); PUMP1(); }
          if (h) PROF(20);
          if (warp < 2) mbar_wait(bar_halo + 8, h);
          if (h) PROF(21);
          if (h == 0) mbar_wait(ub, par);
          FRAG_GET(vf, 1);
#pragma unroll
          for (int o = 1; o <= 2; o <<= 1)
#pragma unroll
            for (int i = 0; i < 4; i++) mx[i >> 1][i & 1] += __shfl_xor_sync(0xffffffffu, mx[i >> 1][i & 1], o);
          float o[8][4];
          uint32_t pa[4][2];
#pragma unroll
          for (int i = 0; i < 4; i++) {
            const float iv = rcp_fast(mx[i >> 1][i & 1]);
            const uint32_t w = pack_bf16(va[i >> 1][i & 1] * iv, vb[i >> 1][i & 1] * iv);
            pa[i][0] = w & msk[0]; pa[i][1] = w & ~msk[0];
          }
          PROFH(7, 19);
#pragma unroll
          for (int i = 7; i >= 0; i--) {
            const uint32_t* a = vf + (i >> 2) * 8 + (i & 3) * 2;
            mma_bf16_z(o[i], a[0], a[1], a[8], a[9], pa[(i & 2) + (i >> 2)][0], pa[(i & 2) + (i >> 2)][1]);
          }
          if (h == 0) PUMPN() else mbar_wait(bar_done + 30 * 8, par);
          if (NLAYERS > 1 && l + h == 0) mbar_wait(bar_phi + 8, 0);
          if (h) PROF(22);
          {
            const uint32_t pm0 = msk[1], pbit = O_BIT(l) * 0x10001u;
#pragma unroll
            for (int i = 0; i < 4; i++)
              stsm_x4_t(ta[i] + (h ? 3 : 12) * SLOT, PBIT(pack_bf16(o[i][0], o[i][1])), PBIT(pack_bf16(o[i + 4][0], o[i + 4][1])),
                        pack_bf16(o[i][2], o[i][3]), pack_bf16(o[i + 4][2], o[i + 4][3]));
          }
          WARP_STORE(&tm_os, sbase + (h ? 3 : 12) * SLOT, jj * 128 + h * 64, mm * 128);
          PROFH(11, 23);
          if (h) break;
          REST_P1(ASKEW);
          asm volatile("cp.async.bulk.wait_group.read 0;" ::: "memory");
          DRAIN_A(S1, 1, {});
        }
      } else {
        constexpr uint32_t par = 1;
        float st[32];
        const float c0 = rs0 * LOG2E, c1 = rs1 * LOG2E;
        { V_ADDR(pV, 0); STAGE_V(S0 + 64); }
        if (warp < 2) sts128(sbase + OFF_ONES + warp * 512 + lane * 16, 0x3F803F80u, 0x3F803F80u, 0x3F803F80u, 0x3F803F80u);
        scale32(st, S0, c0, c1);
        PIN(st, 32);
#define PHI_PIECE(c) { \
          e_[2 * (c)] = ex2(st[2 * (c)]); e_[2 * (c) + 1] = ex2(st[2 * (c) + 1]); \
          _Pragma("unroll") for (int k_ = 4 * (c); k_ < 4 * (c) + 4; k_++) m_[(c) >> 1] = (k_ & 7) ? fmaf(st[k_], st[k_], m_[(c) >> 1]) : st[k_] * st[k_]; \
          asm volatile("" : "+f"(e_[2 * (c)]), "+f"(e_[2 * (c) + 1]), "+f"(m_[(c) >> 1])); SCHED_FENCE(); }
#define PHI_FIN() { \
          big = __any_sync(0xffffffffu, !(fmaxf(fmaxf(m_[0], m_[1]), fmaxf(m_[2], m_[3])) < BIGLIM)); \
          if (__builtin_expect(big, 0)) { COPYN(e_, st, 16); } \
          _Pragma("unroll") for (int k_ = 0; k_ < 16; k_++) st[k_] = e_[k_]; \
          PIN(st, 16); }
#define KV_MMA(vs, IL) { \
          const uint32_t dp = dA0 + 12 * 1024 - wg * 2560, dv = dA0 + (vs) * 1024 + ((OFF_ONES - (vs) * SLOT - 16) << 12) - wg * (512 << 16); \
          STG_WAIT(); \
          wgmma_fence(); \
          _Pragma("unroll") for (int ks = 0; ks < 8; ks++) { \
            const uint64_t a = DESC(dp + ks * 128, 0x40000040), b = DESC(dv + ks * (64 - (64 << 16)), 0x80000020); \
            if ((IL) && ks) wgmma_fence(); \
            if (ks == 0) wgmma_n40<0, 1>(kv, a, b); else wgmma_n40<1, 1>(kv, a, b); \
            if (ks == 7) wgmma_commit(); \
            if (IL) PHI_PIECE(ks); } }
#define KV_RED1(i) if (h) red_v4(g_kv[l >> 1] + (jj * 4) * KVH + warp * 768 + lane * 4 + (i) * 128, S0[32 + (i) * 3], S0[33 + (i) * 3], S0[34 + (i) * 3], 1.f)
#define KV_REDS(n) { _Pragma("unroll") for (int i_ = 0; i_ < 6; i_++) if (((RPACE >> (4 * i_)) & 15) == (n)) KV_RED1(i_); }
#define KV_SEND(kp) { \
          float sd[9]; \
          _Pragma("unroll") for (int i = 0; i < 8; i++) { (kp)[i] = kv[i]; sd[i] = kv[8 + i]; } \
          (kp)[8] = rank ? kv[18] : kv[16]; sd[8] = rank ? kv[16] : kv[18]; \
          const uint32_t ra = sbase + peer + (warp * 32 + lane) * 4, rb = bar_kx + peer; \
          if (elect_one()) mbar_expect_tx(bar_kx, 1152); \
          _Pragma("unroll") for (int i = 0; i < 2; i++) \
            asm volatile("st.async.weak.shared::cluster.mbarrier::complete_tx::bytes.v4.f32 [%0], {%1, %2, %3, %4}, [%5];" \
                         :: "r"(ra + (warp * 32 + lane) * 12 + OFF_PHI + i * 4096), "f"(sd[4 * i]), "f"(sd[4 * i + 1]), "f"(sd[4 * i + 2]), "f"(sd[4 * i + 3]), "r"(rb) : "memory"); \
          asm volatile("st.async.weak.shared::cluster.mbarrier::complete_tx::bytes.f32 [%0], %1, [%2];" :: "r"(ra + OFF_LNB), "f"(sd[8]), "r"(rb) : "memory"); }
#define KV_RECV(kp, hp) { \
          float r_[9]; \
          float* kvg = g_kv[l >> 1] + (jj * 4 + (hp) * 2) * KVH + warp * 768 + rank * 384 + lane * 4; \
          mbar_wait(bar_kx, l >> 1); \
          _Pragma("unroll") for (int i = 0; i < 2; i++) \
            asm volatile("ld.shared.v4.f32 {%0, %1, %2, %3}, [%4];" : "=f"(r_[4 * i]), "=f"(r_[4 * i + 1]), "=f"(r_[4 * i + 2]), "=f"(r_[4 * i + 3]) \
                         : "r"(sbase + OFF_PHI + i * 4096 + (warp * 32 + lane) * 16) : "memory"); \
          r_[8] = lds32f(sbase + OFF_LNB + (warp * 32 + lane) * 4); \
          _Pragma("unroll") for (int i = 0; i < 3; i++) red_v4(kvg + i * 128, (kp)[3 * i] + r_[3 * i], (kp)[3 * i + 1] + r_[3 * i + 1], (kp)[3 * i + 2] + r_[3 * i + 2], 2.f); }
#define KV_LOAD(hp) { \
          const uint4* kvg = reinterpret_cast<const uint4*>(g_kv[l >> 1] + (jj * 4 + (hp) * 2) * KVH) + warp * 192 + lane; \
          _Pragma("unroll") for (int i = 0; i < 6; i++) v[i] = ld_b128(kvg + i * 32); }
#define KVV(i) __uint_as_float((i) % 3 == 0 ? v[(i) / 3].x : ((i) % 3 == 1 ? v[(i) / 3].y : v[(i) / 3].z))
#define KV_TILE(hp) { \
          _Pragma("unroll 1") for (int it = 0; it < (1 << 16); it++) { \
            if (__all_sync(0xffffffffu, (v[0].w & v[1].w & v[2].w & v[3].w & v[4].w & v[5].w) == 0x41800000u)) break; \
            RETRY_COUNT(); \
            KV_LOAD(hp); \
          } \
          if (hp) PROF(26); else PROF(25); \
          const uint32_t e = lane & 7, jt = ((lane >> 1) & 4) + (e >> 1); \
          const uint32_t row = ((((warp >> 1) ^ wg) & 1) << 5) + ((jt & 1) << 4) + ((warp & 1) << 3) + (jt & 6) + (e & 1); \
          const uint32_t kd = pV + wg * 8192 + row * 128, ksw = (row & 7) << 4; \
          _Pragma("unroll") for (int i = 0; i < 2; i++) \
            stsm_x4(kd + ((i * 32 + lhi) ^ ksw), pack_bf16(KVV(i * 9), KVV(i * 9 + 1)), pack_bf16(KVV(i * 9 + 2), KVV(i * 9 + 3)), \
                    pack_bf16(KVV(i * 9 + 4), KVV(i * 9 + 5)), pack_bf16(KVV(i * 9 + 6), KVV(i * 9 + 7))); \
          stsm_x4(kd + ((64u + lhi) ^ ksw), pack_bf16(KVV(8), 1.f), pack_bf16(KVV(17), 1.f), 0u, 0u); }
#pragma unroll 1
        for (int h = 0; h < 2; h++) {
          PROFH(4, 6);
          PUMP0();
          LANE_CONSTS();
          const uint32_t dsw = (uint32_t)(g ^ (2 * t)) << 4, dst = ((t & 2) ? pK : sbase + 12 * SLOT) + (r0 + g) * 128;
          float e[16], f[16];
          KV_REDS(1);
          float sa = exps16_<0>(e, st);
          exps16_fix<0>(e, st, sa);
          asm volatile("" : "+f"(sa)); PIN(e, 16); PUMP0();
          if (h) STG_WAIT();
          KV_REDS(2);
          store16(e, sa, dst, dsw, 4);
          float sb = exps16_<1>(f, st);
          exps16_fix<1>(f, st, sb);
          asm volatile("" : "+f"(sb)); PIN(f, 16); PUMP0();
          KV_REDS(3);
          store16(f, sb, dst, dsw, 0);
          float sc = exps16_<0>(e, st + 2);
          exps16_fix<0>(e, st + 2, sc);
          asm volatile("" : "+f"(sc)); PIN(e, 16); PUMP0();
          KV_REDS(4);
          store16(e, sc, dst + 1024, dsw, 4);
          float sd = exps16_<1>(f, st + 2);
          exps16_fix<1>(f, st + 2, sd);
          asm volatile("" : "+f"(sd)); PIN(f, 16); PUMP0();
          store16(f, sd, dst + 1024, dsw, 0);
          PROFH(5, 7);
          if (h) break;
          {
            float kv[20];
            ACC_DEF(kv, 20);
            fence_proxy_async_smem();
            STG_ARRIVE();
            float e_[16], m_[4];
            KV_MMA(11, 0);
            PUMP0();
            ACC_FENCE(kv, 20);
            STG_ARRIVE();
            scale32(st, S0 + 32, c0, c1);
            PIN(st, 32);
            {
              COPYN(S0 + 32, kv, 8); COPYN(S0 + 40, kv + 16, 1); COPYN(S0 + 41, kv + 8, 8); COPYN(S0 + 49, kv + 18, 1);
              const int h = 1;
              KV_REDS(0);
            }
          }
        }
        bool big;
        uint4 v[6];
        {
          float kv[20];
          { LANE_CONSTS(); KV_LOAD(0); }
          mbar_wait(bar_stat2, par);
          ub = bar_full + 240;
          LNSTEP(S1, 1);
          PUMP1();
          if (wg == 0) bar_sync<BAR_SKEW, 256>();
          QSTEP(S1, RA_CUR, 1);
          if (wg == 1) bar_arrive<BAR_SKEW, 256>();
          QREL();
          { LANE_CONSTS(); KV_TILE(0); }
          LANE_CONSTS();
          V_ADDR(sbase + 3 * SLOT, rank * 32);
          PINU(va_, 2);
          mbar_wait(bar_done + 30 * 8, par);
          wgmma_wait<0>();
          ACC_FENCE(S1, 96);
          PROF(13);
          STAGE_V(S1 + 64);
          fence_proxy_async_smem();
          STG_ARRIVE();
          REL(bar_done + 31 * 8);
          scale32(st, S1, c0, c1);
          PIN(st, 32);
          PROF(16);
          ACC_DEF(kv, 20);
          float e_[16], m_[4];
          KV_MMA(3, 1);
          SCHED_FENCE();
          PROF(14);
          PHI_FIN();
          SCHED_FENCE();
          PROF(15);
          wgmma_wait<0>();
          ACC_FENCE(kv, 20);
          PROF(12);
          { float kp[9]; KV_SEND(kp); _Pragma("unroll") for (int i = 0; i < 3; i++) v[i] = make_uint4(__float_as_uint(kp[3 * i]), __float_as_uint(kp[3 * i + 1]), __float_as_uint(kp[3 * i + 2]), 0u); }
#define VDEF(i0) _Pragma("unroll") for (int i = (i0); i < 6; i++) asm volatile("" : "=r"(v[i].x), "=r"(v[i].y), "=r"(v[i].z), "=r"(v[i].w))
          VDEF(3);
          PROF(17);
        }
#pragma unroll 1
        for (int h = 0; h < 2; h++) {
          const uint32_t pO = sbase + (h ? 3 : 8) * SLOT;
          LANE_CONSTS();
          uint32_t fq[32];
          if (h) { KV_LOAD(1); phiq_a(st, big); PIN(st, 16); PROF(31); }
          PROFH(18, 32);
          SCHED_FENCE();
          phiq_b<1>(fq, st, big); PINU(fq, 16); PIN(st + 16, 16);
          SCHED_FENCE();
          PROFH(8, 9);
          if (h) {
            asm volatile("cp.async.bulk.wait_group.read 0;" ::: "memory");
            mbar_wait(bar_lx, par);
            PROF(30);
            KV_TILE(1);
            fence_proxy_async_smem();
            STG_ARRIVE();
          }
          SCHED_FENCE();
          if (h == 0) {
            float kp[9];
#pragma unroll
            for (int i = 0; i < 9; i++) kp[i] = KVV(i);
            KV_RECV(kp, 1);
            SCHED_FENCE();
          }
          phiq_b<0>(fq + 16, st + 16, big); PINU(fq + 16, 16);
          PROFH(10, 21);
          if (h) STG_WAIT();
          wgmma_wait<0>();
          ACC_FENCE(S1, 64);
          PROFH(19, 33);
          float o[4][20];
#define O_MMA(hh) { \
            const uint64_t db = make_desc(pV + (hh) * 8192, 16, 1024); \
            ACC_DEF(o[(hh) * 2], 20); ACC_DEF(o[(hh) * 2 + 1], 20); \
            wgmma_fence(); \
            wgmma_n40_rs<0>(o[(hh) * 2], fq + (hh) * 16, db + 256); wgmma_n40_rs<0>(o[(hh) * 2 + 1], fq + (hh) * 16 + 8, db); \
            wgmma_n40_rs<1>(o[(hh) * 2], fq + (hh) * 16 + 4, db + 384); wgmma_n40_rs<1>(o[(hh) * 2 + 1], fq + (hh) * 16 + 12, db + 128); \
            wgmma_commit(); }
          O_MMA(0);
          SCHED_FENCE();
          PMASKS(true, O_BIT(l));
#pragma unroll
          for (int hh = 0; hh < 2; hh++) {
            wgmma_wait<0>();
            ACC_FENCE(o[hh * 2], 20); ACC_FENCE(o[hh * 2 + 1], 20);
            if (!hh) { O_MMA(1); SCHED_FENCE(); }
            if (hh) PROFH(22, 24);
            const float* x = o[hh * 2];
            const float* y = o[hh * 2 + 1];
            const float sx0 = x[17] * 0x1p-40f, sy0 = y[17] * 0x1p-40f, sx1 = x[19] * 0x1p-40f, sy1 = y[19] * 0x1p-40f;
            const float i0 = rcp_fast(fmaf(fmaf(x[17], 1e-6f, x[16]), sy0, y[16] * sx0)), i1 = rcp_fast(fmaf(fmaf(x[19], 1e-6f, x[18]), sy1, y[18] * sx1));
            const float ax0 = sy0 * i0, ay0 = sx0 * i0, ax1 = sy1 * i1, ay1 = sx1 * i1;
#pragma unroll
            for (int dp = 0; dp < 2; dp++)
              stsm_x4(pO + srowoff + ((hh * 64 + dp * 32 + lhi) ^ lsw),
                      PBIT(pack_bf16(fmaf(x[dp * 8], ax0, y[dp * 8] * ay0), fmaf(x[dp * 8 + 1], ax0, y[dp * 8 + 1] * ay0))),
                      PBIT(pack_bf16(fmaf(x[dp * 8 + 2], ax1, y[dp * 8 + 2] * ay1), fmaf(x[dp * 8 + 3], ax1, y[dp * 8 + 3] * ay1))),
                      (pack_bf16(fmaf(x[dp * 8 + 4], ax0, y[dp * 8 + 4] * ay0), fmaf(x[dp * 8 + 5], ax0, y[dp * 8 + 5] * ay0))),
                      (pack_bf16(fmaf(x[dp * 8 + 6], ax1, y[dp * 8 + 6] * ay1), fmaf(x[dp * 8 + 7], ax1, y[dp * 8 + 7] * ay1))));
          }
          WARP_STORE(&tm_os, pO, jj * 128 + h * 64, mm * 128);
          PROFH(20, 34);
          if (h) break;
          float T_[64];
          scale32(st, S1 + 32, c0, c1);
          PIN(st, 32);
          ACC_DEF(T_, 64);
          XM_ISSUE(); wgmma_commit();
          SCHED_FENCE();
          big = any_big(st);
          SCHED_FENCE();
          PROF(27);
          wgmma_wait<0>(); XM_DONE();
          PROF(28);
          bar_wg(wg);
          WSTEP();
          SCHED_FENCE();
          VDEF(0);
          PROF(29);
        }
      }
      __syncwarp();
      if (elect_one()) mbar_arrive_local(bar_epi);
      bar_wg(wg);
#pragma unroll 1
      while (ub < bar_full + 384) {
        WSTEP();
        if (ub == bar_full + 8 * 41) { asm volatile("cp.async.bulk.wait_group.read 0;" ::: "memory"); PROF(35); }
        if (ub == bar_full + 8 * 42) PROF(36);
      }
      {
        float Wb[32];
        LANE_CONSTS();
        TILE_CONSTS(pK, l < NLAYERS - 1, X_BIT(l));
        if (l < NLAYERS - 1) mbar_wait(bar_full, par ^ 1);
        wgmma_wait<0>();
        ACC_FENCE(S1, 64);
        COPYN(Wb, S1 + 32, 32);
        PROF(37);
        X_OUT(0, S1);
        if (l == NLAYERS - 1) {
          int w; asm volatile("mov.u32 %0, %1;" : "=r"(w) : "r"(warp));
          const int oc = jj * 128 + (w & 1) * 1024, orow = mm * 64 + (w >> 1) * 16 - r0;
          WARP_STORE(&tm_xo, pK, oc, orow);
          { PMASKS(false, 0); X_OUT(1, Wb); }
          WARP_STORE(&tm_xo, pV, oc + 64, orow);
          break;
        }
        WARP_STORE(&tm_os, pK, jj * 128, mm * 128 + S_LEN);
        PROF(38);
        bar_wg(wg);
        FIRST_STEP(l + 1);
        REL(bar_done + 47 * 8);
        PROF(39);
        { PMASKS(false, 0); X_OUT(1, Wb); }
        fence_proxy_async_smem();
      }
    }
    asm volatile("cp.async.bulk.wait_group.read 0;" ::: "memory");
    cluster_sync();
  }
}

typedef CUresult (*PFN_encode)(CUtensorMap*, CUtensorMapDataType, cuuint32_t, void*, const cuuint64_t*, const cuuint64_t*,
                               const cuuint32_t*, const cuuint32_t*, CUtensorMapInterleave, CUtensorMapSwizzle,
                               CUtensorMapL2promotion, CUtensorMapFloatOOBfill);

CUtensorMap make_map(PFN_encode enc, const void* ptr, uint64_t inner, uint64_t outer, uint32_t box_inner, uint32_t box_outer,
                     CUtensorMapSwizzle swz = CU_TENSOR_MAP_SWIZZLE_128B, int promo = CU_TENSOR_MAP_L2_PROMOTION_L2_256B) {
  CUtensorMap m;
  cuuint64_t dims[2] = {inner, outer};
  cuuint64_t strides[1] = {inner * 2};
  cuuint32_t box[2] = {box_inner, box_outer};
  cuuint32_t es[2] = {1, 1};
  enc(&m, CU_TENSOR_MAP_DATA_TYPE_BFLOAT16, 2, const_cast<void*>(ptr), dims, strides, box, es, CU_TENSOR_MAP_INTERLEAVE_NONE,
      swz, (CUtensorMapL2promotion)promo, CU_TENSOR_MAP_FLOAT_OOB_FILL_NONE);
  return m;
}

CUtensorMap make_tile_map(PFN_encode enc, const void* ptr, uint64_t rows, bool by_parity, int promo) {
  CUtensorMap m;
  cuuint64_t dims[4] = {D_MODEL, 16, 2, rows / 32};
  cuuint64_t strides[3] = {by_parity ? 4096u : 2048u, by_parity ? 2048u : 32768u, 65536};
  cuuint32_t box[4] = {64, 16, 2, 4};
  cuuint32_t es[4] = {1, 1, 1, 1};
  enc(&m, CU_TENSOR_MAP_DATA_TYPE_BFLOAT16, 4, const_cast<void*>(ptr), dims, strides, box, es, CU_TENSOR_MAP_INTERLEAVE_NONE,
      CU_TENSOR_MAP_SWIZZLE_128B, (CUtensorMapL2promotion)promo, CU_TENSOR_MAP_FLOAT_OOB_FILL_NONE);
  return m;
}

}

extern "C" void kernel_launch(void* const* d_in, const int* in_sizes, int n_in, void* d_out, int out_size) {
  (void)in_sizes; (void)n_in; (void)out_size;
  static PFN_encode enc = nullptr;
  if (!enc) {
    void* fn = nullptr;
    cudaDriverEntryPointQueryResult qr;
    cudaGetDriverEntryPoint("cuTensorMapEncodeTiled", &fn, cudaEnableDefault, &qr);
    enc = (PFN_encode)fn;
    cudaFuncSetAttribute(mega_kernel, cudaFuncAttributeMaxDynamicSharedMemorySize, SMEM_BYTES);
  }
  Params prm;
  prm.x0 = (const __nv_bfloat16*)d_in[0];
  prm.wA_qkv = (const __nv_bfloat16*)d_in[1];
  prm.wA_o = (const __nv_bfloat16*)d_in[2];
  prm.wB_qkv = (const __nv_bfloat16*)d_in[4];
  prm.wB_phi = (const __nv_bfloat16*)d_in[5];
  prm.wB_o = (const __nv_bfloat16*)d_in[6];
  prm.out = (__nv_bfloat16*)d_out;
  void *obuf = nullptr, *wf = nullptr;
  cudaGetSymbolAddress(&obuf, g_obuf);
  cudaGetSymbolAddress(&wf, g_wfold);
  CUtensorMap tm_x0 = make_tile_map(enc, d_in[0], S_LEN, true, XPROMO);
  CUtensorMap tm_xo = make_map(enc, d_out, 2 * D_MODEL, S_LEN / 2, 64, 16);
  CUtensorMap tm_os = make_map(enc, obuf, D_MODEL, 2 * S_LEN, 64, 16);
  CUtensorMap tm_o = make_tile_map(enc, obuf, 2 * S_LEN, false, OPROMO);
  CUtensorMap tm_wf = make_map(enc, wf, 2048, D_MODEL, 64, 32);
  CUtensorMap tm_wqA = make_map(enc, d_in[1], 3 * D_MODEL, D_MODEL, 64, 32, CU_TENSOR_MAP_SWIZZLE_128B, WPROMO);
  CUtensorMap tm_wqB = make_map(enc, prm.wB_qkv, 3 * D_MODEL, D_MODEL, 64, 32);
  CUtensorMap tm_woA = make_map(enc, prm.wA_o, D_MODEL, D_MODEL, 64, 64);
  CUtensorMap tm_woB = make_map(enc, prm.wB_o, D_MODEL, D_MODEL, 64, 64);
  CUtensorMap tm_phi = make_map(enc, prm.wB_phi, 32, 1024, 32, 128, CU_TENSOR_MAP_SWIZZLE_64B);
  mega_kernel<<<NMAIN + NAUX, 384, SMEM_BYTES>>>(tm_x0, tm_xo, tm_os, tm_o, tm_wf, tm_wqA, tm_wqB, tm_woA, tm_woB, tm_phi, prm);
}
```

```cpp
#include <cuda_runtime.h>
#include <cuda.h>
#include <cuda_bf16.h>
#include <stdint.h>

#define NLAYERS 4

#define HPUMP2 1
#define ASKEW 2
#define FPUMP 3
#define PFGAP 100
#define POLLGAP 120
#define HW1 29
#define XPACE 0x06050401000000ull
#define HW0 18
#define XD 4
#define WFGAP 50
#define EARLY 2
#define BIGLIM 3600.f
#define SUMLO 0x1p-100f
#define SUMHI 0x1p100f
#define XPROMO 2
#define OPROMO 3
#define STAG2 300
#define WPROMO 3
#define SB0 2
#define SB1 4
#define SB2 6
#define PROWS 3
#define SPD0 0
#define SPD1 0
#define SPD2 300
#define FRB 0x3535353535ull
#define NOB 0xFFFFFF00u
#define NO1 ~0u
#define NOX ~0u
#define FD0 0
#define FD1 3
#define RPACE 0x221100
namespace {

constexpr int S_LEN = 2048, D_MODEL = 1024;
constexpr int NAUX = 4, NMAIN = 128;
constexpr int SLOT = 16384;
constexpr int QST = 24576;
constexpr int OFF_RA = 6 * SLOT, OFF_S = 10 * SLOT;
constexpr int OFF_HALO = 13 * SLOT, OFF_LNB = OFF_HALO  , OFF_ONES = OFF_HALO + 3072;
constexpr int OFF_ST = OFF_HALO + 7168  , OFF_ID = OFF_HALO + 7680, OFF_PHI = OFF_HALO + 8192;
constexpr int OFF_BAR = 14 * SLOT;
constexpr int OFF_LNA = OFF_BAR + 1024;
constexpr int SMEM_BYTES = OFF_LNA + 2048;
#define WO_ASLOT(par) ((par) ? 0x9876CAB39876CA98ull : 0xBC7698A3BC7698BCull)
constexpr unsigned long long WO_BSLOT = 0x5432105421054210ull;
__device__ __forceinline__ int srcb(int j, int i) { return (i + (i >= j)) & 7; }
__device__ __forceinline__ int kslice(int j, int i) { return i < 2 ? 2 * j + i : (i < 9 ? 2 * srcb(j, i - 2) : 2 * srcb(j, i - 9) + 1); }
__device__ __forceinline__ int wslice(int j, int s) { return 2 * ((s & 7) ? srcb(j, (s & 7) - 1) : j) + (s >> 3); }
constexpr int KVH = 6 * 128 * 4;

struct __align__(128) Flag { unsigned v; unsigned pad[31]; };
struct Flags {
  Flag xready[4][16];
  Flag wfready[8];
  Flag done;
  Flag epoch;
};

__device__ Flags g_flags;
__device__ __nv_bfloat16 g_obuf[2 * S_LEN * D_MODEL];
#define O_BIT(l) ((epoch * NLAYERS + (l) + 1) & 1u)
#define X_BIT(l) ((epoch * (NLAYERS - 1) + (l) + 1) & 1u)
__device__ __nv_bfloat16 g_wfold[D_MODEL * 2048];
__device__ uint4 g_halo[16 * 8 * 512];
__device__ __align__(128) float g_kv[2][32 * KVH];
__device__ __align__(128) uint2 g_colsum[2][1536][2];
__device__ __align__(128) uint2 g_stats[S_LEN * 8];
#define H_BIT(l) (NLAYERS > 2 ? (uint32_t)((l) == 0) : (ep1 & 1))
#define STAT_TAG(l) ((ep1 * NLAYERS + (l) + 1) & 3u)

#define RETRY_COUNT()
#define PRL 0
#define PRU 0
#define PROFL 1
#define PROFW 0
#define PROFT(i) do {} while (0)
#define PROF(i) do {} while (0)
#define PROFH(i, j) do {} while (0)

__device__ __forceinline__ uint32_t smem_u32(const void* p) { return (uint32_t)__cvta_generic_to_shared(p); }
__device__ __forceinline__ bool elect_one() {
  uint32_t p;
  asm volatile("{\n.reg .pred p;\nelect.sync _|p, 0xffffffff;\nselp.u32 %0, 1, 0, p;\n}\n" : "=r"(p));
  return p != 0;
}
__device__ __forceinline__ void mbar_init(uint32_t bar, uint32_t cnt) {
  asm volatile("mbarrier.init.shared::cta.b64 [%0], %1;" :: "r"(bar), "r"(cnt));
}
__device__ __forceinline__ void mbar_expect_tx(uint32_t bar, uint32_t bytes) {
  asm volatile("mbarrier.arrive.expect_tx.shared::cta.b64 _, [%0], %1;" :: "r"(bar), "r"(bytes) : "memory");
}
#define mbar_wait(bar, parity) \
  asm volatile("{\n.reg .pred p, q;\nW_%=:\nmbarrier.try_wait.parity.shared::cta.b64 p, [%1], %2;\nadd.s32 %0, %0, -1;\n" \
               "setp.gt.and.s32 q, %0, 0, !p;\n@q bra.uni W_%=;\n}\n" : "+r"(budget) : "r"((uint32_t)(bar)), "r"((uint32_t)(parity)) : "memory")
#define mbar_wait_sl(bar, parity) \
  asm volatile("{\n.reg .pred p, q;\nW_%=:\nmbarrier.try_wait.parity.shared::cta.b64 p, [%1], %2, 20000;\nadd.s32 %0, %0, -64;\n" \
               "setp.gt.and.s32 q, %0, 0, !p;\n@q bra.uni W_%=;\n}\n" : "+r"(budget) : "r"((uint32_t)(bar)), "r"((uint32_t)(parity)) : "memory")
__device__ __forceinline__ void mbar_arrive_local(uint32_t bar) {
  asm volatile("mbarrier.arrive.shared::cta.b64 _, [%0];" :: "r"(bar) : "memory");
}
__device__ __forceinline__ void tma_load_2d(uint32_t dst, const CUtensorMap* tm, uint32_t bar, int c0, int c1) {
  asm volatile("cp.async.bulk.tensor.2d.shared::cluster.global.mbarrier::complete_tx::bytes [%0], [%1, {%3, %4}], [%2];"
               :: "r"(dst), "l"(tm), "r"(bar), "r"(c0), "r"(c1) : "memory");
}
__device__ __forceinline__ void tma_load_2d_mc(uint32_t dst, const CUtensorMap* tm, uint32_t bar, int c0, int c1) {
  asm volatile("cp.async.bulk.tensor.2d.shared::cluster.global.mbarrier::complete_tx::bytes.multicast::cluster [%0], [%1, {%3, %4}], [%2], %5;"
               :: "r"(dst), "l"(tm), "r"(bar), "r"(c0), "r"(c1), "h"((uint16_t)3) : "memory");
}
__device__ __forceinline__ void tma_store_2d(const CUtensorMap* tm, uint32_t src, int c0, int c1) {
  asm volatile("cp.async.bulk.tensor.2d.global.shared::cta.bulk_group [%0, {%2, %3}], [%1];"
               :: "l"(tm), "r"(src), "r"(c0), "r"(c1) : "memory");
}
__device__ __forceinline__ void tma_load_t(uint32_t dst, const CUtensorMap* tm, uint32_t bar, int c0, int row) {
  asm volatile("cp.async.bulk.tensor.4d.shared::cluster.global.mbarrier::complete_tx::bytes [%0], [%1, {%3, %5, %5, %4}], [%2];"
               :: "r"(dst), "l"(tm), "r"(bar), "r"(c0), "r"(row >> 5), "r"(0) : "memory");
}
__device__ __forceinline__ void tma_store_t(const CUtensorMap* tm, uint32_t src, int c0, int row) {
  asm volatile("cp.async.bulk.tensor.4d.global.shared::cta.bulk_group [%0, {%2, %4, %4, %3}], [%1];"
               :: "l"(tm), "r"(src), "r"(c0), "r"(row >> 5), "r"(0) : "memory");
}
__device__ __forceinline__ void bulk_commit_wait() {
  asm volatile("cp.async.bulk.commit_group;\ncp.async.bulk.wait_group 0;" ::: "memory");
}
__device__ __forceinline__ void prefetch_tmap(const CUtensorMap* tm) {
  asm volatile("prefetch.tensormap [%0];" :: "l"(tm) : "memory");
}
__device__ __forceinline__ void fence_proxy_async_global() { asm volatile("fence.proxy.async.global;" ::: "memory"); }
__device__ __forceinline__ void fence_proxy_async_smem() { asm volatile("fence.proxy.async.shared::cta;" ::: "memory"); }
__device__ __forceinline__ unsigned ld_relaxed(const unsigned* p) {
  unsigned v;
  asm volatile("ld.relaxed.gpu.global.u32 %0, [%1];" : "=r"(v) : "l"(p) : "memory");
  return v;
}
__device__ __forceinline__ void fence_acquire() { asm volatile("fence.acquire.gpu;" ::: "memory"); }
__device__ __forceinline__ void wait_flag(const unsigned* p, unsigned target) {
  int it = 0;
  while ((int)(ld_relaxed(p) - target) < 0 && ++it < (1 << 20)) {}
  fence_acquire();
}
__device__ __forceinline__ void signal_release(unsigned* p) {
  asm volatile("red.release.gpu.global.add.u32 [%0], 1;" :: "l"(p) : "memory");
}
template <int ID, int N> __device__ __forceinline__ void bar_arrive() { asm volatile("bar.arrive %0, %1;" :: "n"(ID), "n"(N) : "memory"); }
template <int ID, int N> __device__ __forceinline__ void bar_sync() { asm volatile("bar.sync %0, %1;" :: "n"(ID), "n"(N) : "memory"); }
__device__ __forceinline__ void bar_wg(int wg) { asm volatile("bar.sync %0, 128;" :: "r"(2 + wg) : "memory"); }
__device__ __forceinline__ void cluster_sync() {
  asm volatile("barrier.cluster.arrive.relaxed.aligned;\nbarrier.cluster.wait.aligned;" ::: "memory");
}
__device__ __forceinline__ void cluster_wait() { asm volatile("barrier.cluster.wait.acquire.aligned;" ::: "memory"); }
enum { BAR_X1 = 7, BAR_WF = 8  , BAR_SKEW = 10 };

__device__ __forceinline__ void wgmma_fence() { asm volatile("wgmma.fence.sync.aligned;" ::: "memory"); }
__device__ __forceinline__ void wgmma_commit() { asm volatile("wgmma.commit_group.sync.aligned;" ::: "memory"); }
template <int N> __device__ __forceinline__ void wgmma_wait() { asm volatile("wgmma.wait_group.sync.aligned %0;" :: "n"(N) : "memory"); }

template <int scale_d, int tnsp_b = 1> __device__ __forceinline__ void wgmma_n192(float* d, uint64_t descA, uint64_t descB) {
  asm volatile("{\n.reg .pred p;\nsetp.ne.b32 p, %98, 0;\n"
               "wgmma.mma_async.sync.aligned.m64n192k16.f32.bf16.bf16 {%0,%1,%2,%3,%4,%5,%6,%7,%8,%9,%10,%11,%12,%13,%14,%15,%16,%17,%18,%19,%20,%21,%22,%23,%24,%25,%26,%27,%28,%29,%30,%31,%32,%33,%34,%35,%36,%37,%38,%39,%40,%41,%42,%43,%44,%45,%46,%47,%48,%49,%50,%51,%52,%53,%54,%55,%56,%57,%58,%59,%60,%61,%62,%63,%64,%65,%66,%67,%68,%69,%70,%71,%72,%73,%74,%75,%76,%77,%78,%79,%80,%81,%82,%83,%84,%85,%86,%87,%88,%89,%90,%91,%92,%93,%94,%95}, %96, %97, p, 1, 1, 0, %99;\n}\n"
               : "+f"(d[0]), "+f"(d[1]), "+f"(d[2]), "+f"(d[3]), "+f"(d[4]), "+f"(d[5]), "+f"(d[6]), "+f"(d[7]), "+f"(d[8]), "+f"(d[9]), "+f"(d[10]), "+f"(d[11]), "+f"(d[12]), "+f"(d[13]), "+f"(d[14]), "+f"(d[15]), "+f"(d[16]), "+f"(d[17]), "+f"(d[18]), "+f"(d[19]), "+f"(d[20]), "+f"(d[21]), "+f"(d[22]), "+f"(d[23]), "+f"(d[24]), "+f"(d[25]), "+f"(d[26]), "+f"(d[27]), "+f"(d[28]), "+f"(d[29]), "+f"(d[30]), "+f"(d[31]), "+f"(d[32]), "+f"(d[33]), "+f"(d[34]), "+f"(d[35]), "+f"(d[36]), "+f"(d[37]), "+f"(d[38]), "+f"(d[39]), "+f"(d[40]), "+f"(d[41]), "+f"(d[42]), "+f"(d[43]), "+f"(d[44]), "+f"(d[45]), "+f"(d[46]), "+f"(d[47]), "+f"(d[48]), "+f"(d[49]), "+f"(d[50]), "+f"(d[51]), "+f"(d[52]), "+f"(d[53]), "+f"(d[54]), "+f"(d[55]), "+f"(d[56]), "+f"(d[57]), "+f"(d[58]), "+f"(d[59]), "+f"(d[60]), "+f"(d[61]), "+f"(d[62]), "+f"(d[63]), "+f"(d[64]), "+f"(d[65]), "+f"(d[66]), "+f"(d[67]), "+f"(d[68]), "+f"(d[69]), "+f"(d[70]), "+f"(d[71]), "+f"(d[72]), "+f"(d[73]), "+f"(d[74]), "+f"(d[75]), "+f"(d[76]), "+f"(d[77]), "+f"(d[78]), "+f"(d[79]), "+f"(d[80]), "+f"(d[81]), "+f"(d[82]), "+f"(d[83]), "+f"(d[84]), "+f"(d[85]), "+f"(d[86]), "+f"(d[87]), "+f"(d[88]), "+f"(d[89]), "+f"(d[90]), "+f"(d[91]), "+f"(d[92]), "+f"(d[93]), "+f"(d[94]), "+f"(d[95])
               : "l"(descA), "l"(descB), "n"(scale_d), "n"(tnsp_b));
}
template <int scale_d> __device__ __forceinline__ void wgmma4_n192(float* d, uint32_t da, uint32_t db) {
#define R_ "{%0,%1,%2,%3,%4,%5,%6,%7,%8,%9,%10,%11,%12,%13,%14,%15,%16,%17,%18,%19,%20,%21,%22,%23,%24,%25,%26,%27,%28,%29,%30,%31,%32,%33,%34,%35,%36,%37,%38,%39,%40,%41,%42,%43,%44,%45,%46,%47,%48,%49,%50,%51,%52,%53,%54,%55,%56,%57,%58,%59,%60,%61,%62,%63,%64,%65,%66,%67,%68,%69,%70,%71,%72,%73,%74,%75,%76,%77,%78,%79,%80,%81,%82,%83,%84,%85,%86,%87,%88,%89,%90,%91,%92,%93,%94,%95}"
  asm volatile("{\n.reg .pred p, q;\n.reg .b64 a, b;\nsetp.ne.b32 p, %98, 0;\nsetp.eq.b32 q, 0, 0;\nmov.b64 a, {%96, 0x40000040};\nmov.b64 b, {%97, 0x40000040};\n"
               "wgmma.mma_async.sync.aligned.m64n192k16.f32.bf16.bf16 " R_ ", a, b, p, 1, 1, 0, 1;\nadd.s64 a, a, 2;\nadd.s64 b, b, 128;\n"
               "wgmma.mma_async.sync.aligned.m64n192k16.f32.bf16.bf16 " R_ ", a, b, q, 1, 1, 0, 1;\nadd.s64 a, a, 2;\nadd.s64 b, b, 128;\n"
               "wgmma.mma_async.sync.aligned.m64n192k16.f32.bf16.bf16 " R_ ", a, b, q, 1, 1, 0, 1;\nadd.s64 a, a, 2;\nadd.s64 b, b, 128;\n"
               "wgmma.mma_async.sync.aligned.m64n192k16.f32.bf16.bf16 " R_ ", a, b, q, 1, 1, 0, 1;\n}\n"
               : "+f"(d[0]), "+f"(d[1]), "+f"(d[2]), "+f"(d[3]), "+f"(d[4]), "+f"(d[5]), "+f"(d[6]), "+f"(d[7]), "+f"(d[8]), "+f"(d[9]), "+f"(d[10]), "+f"(d[11]), "+f"(d[12]), "+f"(d[13]), "+f"(d[14]), "+f"(d[15]), "+f"(d[16]), "+f"(d[17]), "+f"(d[18]), "+f"(d[19]), "+f"(d[20]), "+f"(d[21]), "+f"(d[22]), "+f"(d[23]), "+f"(d[24]), "+f"(d[25]), "+f"(d[26]), "+f"(d[27]), "+f"(d[28]), "+f"(d[29]), "+f"(d[30]), "+f"(d[31]), "+f"(d[32]), "+f"(d[33]), "+f"(d[34]), "+f"(d[35]), "+f"(d[36]), "+f"(d[37]), "+f"(d[38]), "+f"(d[39]), "+f"(d[40]), "+f"(d[41]), "+f"(d[42]), "+f"(d[43]), "+f"(d[44]), "+f"(d[45]), "+f"(d[46]), "+f"(d[47]), "+f"(d[48]), "+f"(d[49]), "+f"(d[50]), "+f"(d[51]), "+f"(d[52]), "+f"(d[53]), "+f"(d[54]), "+f"(d[55]), "+f"(d[56]), "+f"(d[57]), "+f"(d[58]), "+f"(d[59]), "+f"(d[60]), "+f"(d[61]), "+f"(d[62]), "+f"(d[63]), "+f"(d[64]), "+f"(d[65]), "+f"(d[66]), "+f"(d[67]), "+f"(d[68]), "+f"(d[69]), "+f"(d[70]), "+f"(d[71]), "+f"(d[72]), "+f"(d[73]), "+f"(d[74]), "+f"(d[75]), "+f"(d[76]), "+f"(d[77]), "+f"(d[78]), "+f"(d[79]), "+f"(d[80]), "+f"(d[81]), "+f"(d[82]), "+f"(d[83]), "+f"(d[84]), "+f"(d[85]), "+f"(d[86]), "+f"(d[87]), "+f"(d[88]), "+f"(d[89]), "+f"(d[90]), "+f"(d[91]), "+f"(d[92]), "+f"(d[93]), "+f"(d[94]), "+f"(d[95])
               : "r"(da), "r"(db), "n"(scale_d));
#undef R_
}
template <int scale_d> __device__ __forceinline__ void wgmma4_n128(float* d, uint32_t da, uint32_t db) {
#define R_ "{%0,%1,%2,%3,%4,%5,%6,%7,%8,%9,%10,%11,%12,%13,%14,%15,%16,%17,%18,%19,%20,%21,%22,%23,%24,%25,%26,%27,%28,%29,%30,%31,%32,%33,%34,%35,%36,%37,%38,%39,%40,%41,%42,%43,%44,%45,%46,%47,%48,%49,%50,%51,%52,%53,%54,%55,%56,%57,%58,%59,%60,%61,%62,%63}"
  asm volatile("{\n.reg .pred p, q;\n.reg .b64 a, b;\nsetp.ne.b32 p, %66, 0;\nsetp.eq.b32 q, 0, 0;\nmov.b64 a, {%64, 0x40000040};\nmov.b64 b, {%65, 0x40000040};\n"
               "wgmma.mma_async.sync.aligned.m64n128k16.f32.bf16.bf16 " R_ ", a, b, p, 1, 1, 0, 1;\nadd.s64 a, a, 2;\nadd.s64 b, b, 128;\n"
               "wgmma.mma_async.sync.aligned.m64n128k16.f32.bf16.bf16 " R_ ", a, b, q, 1, 1, 0, 1;\nadd.s64 a, a, 2;\nadd.s64 b, b, 128;\n"
               "wgmma.mma_async.sync.aligned.m64n128k16.f32.bf16.bf16 " R_ ", a, b, q, 1, 1, 0, 1;\nadd.s64 a, a, 2;\nadd.s64 b, b, 128;\n"
               "wgmma.mma_async.sync.aligned.m64n128k16.f32.bf16.bf16 " R_ ", a, b, q, 1, 1, 0, 1;\n}\n"
               : "+f"(d[0]), "+f"(d[1]), "+f"(d[2]), "+f"(d[3]), "+f"(d[4]), "+f"(d[5]), "+f"(d[6]), "+f"(d[7]), "+f"(d[8]), "+f"(d[9]), "+f"(d[10]), "+f"(d[11]), "+f"(d[12]), "+f"(d[13]), "+f"(d[14]), "+f"(d[15]), "+f"(d[16]), "+f"(d[17]), "+f"(d[18]), "+f"(d[19]), "+f"(d[20]), "+f"(d[21]), "+f"(d[22]), "+f"(d[23]), "+f"(d[24]), "+f"(d[25]), "+f"(d[26]), "+f"(d[27]), "+f"(d[28]), "+f"(d[29]), "+f"(d[30]), "+f"(d[31]), "+f"(d[32]), "+f"(d[33]), "+f"(d[34]), "+f"(d[35]), "+f"(d[36]), "+f"(d[37]), "+f"(d[38]), "+f"(d[39]), "+f"(d[40]), "+f"(d[41]), "+f"(d[42]), "+f"(d[43]), "+f"(d[44]), "+f"(d[45]), "+f"(d[46]), "+f"(d[47]), "+f"(d[48]), "+f"(d[49]), "+f"(d[50]), "+f"(d[51]), "+f"(d[52]), "+f"(d[53]), "+f"(d[54]), "+f"(d[55]), "+f"(d[56]), "+f"(d[57]), "+f"(d[58]), "+f"(d[59]), "+f"(d[60]), "+f"(d[61]), "+f"(d[62]), "+f"(d[63])
               : "r"(da), "r"(db), "n"(scale_d));
#undef R_
}
template <int scale_d> __device__ __forceinline__ void wgmma_n32(float* d, uint64_t descA, uint64_t descB) {
  asm volatile("{\n.reg .pred p;\nsetp.ne.b32 p, %18, 0;\n"
               "wgmma.mma_async.sync.aligned.m64n32k16.f32.bf16.bf16 {%0,%1,%2,%3,%4,%5,%6,%7,%8,%9,%10,%11,%12,%13,%14,%15}, %16, %17, p, 1, 1, 0, 1;\n}\n"
               : "+f"(d[0]), "+f"(d[1]), "+f"(d[2]), "+f"(d[3]), "+f"(d[4]), "+f"(d[5]), "+f"(d[6]), "+f"(d[7]), "+f"(d[8]), "+f"(d[9]), "+f"(d[10]), "+f"(d[11]), "+f"(d[12]), "+f"(d[13]), "+f"(d[14]), "+f"(d[15])
               : "l"(descA), "l"(descB), "n"(scale_d));
}
template <int scale_d, int tnsp_a> __device__ __forceinline__ void wgmma_n40(float* d, uint64_t descA, uint64_t descB) {
  asm volatile("{\n.reg .pred p;\nsetp.ne.b32 p, %22, 0;\n"
               "wgmma.mma_async.sync.aligned.m64n40k16.f32.bf16.bf16 {%0,%1,%2,%3,%4,%5,%6,%7,%8,%9,%10,%11,%12,%13,%14,%15,%16,%17,%18,%19}, %20, %21, p, 1, 1, %23, 1;\n}\n"
               : "+f"(d[0]), "+f"(d[1]), "+f"(d[2]), "+f"(d[3]), "+f"(d[4]), "+f"(d[5]), "+f"(d[6]), "+f"(d[7]), "+f"(d[8]), "+f"(d[9]), "+f"(d[10]), "+f"(d[11]), "+f"(d[12]), "+f"(d[13]), "+f"(d[14]), "+f"(d[15]), "+f"(d[16]), "+f"(d[17]), "+f"(d[18]), "+f"(d[19])
               : "l"(descA), "l"(descB), "n"(scale_d), "n"(tnsp_a));
}
template <int scale_d> __device__ __forceinline__ void wgmma_n40_rs(float* d, const uint32_t* a, uint64_t descB) {
  asm volatile("{\n.reg .pred p;\nsetp.ne.b32 p, %25, 0;\n"
               "wgmma.mma_async.sync.aligned.m64n40k16.f32.bf16.bf16 {%0,%1,%2,%3,%4,%5,%6,%7,%8,%9,%10,%11,%12,%13,%14,%15,%16,%17,%18,%19}, {%20,%21,%22,%23}, %24, p, 1, 1, 1;\n}\n"
               : "+f"(d[0]), "+f"(d[1]), "+f"(d[2]), "+f"(d[3]), "+f"(d[4]), "+f"(d[5]), "+f"(d[6]), "+f"(d[7]), "+f"(d[8]), "+f"(d[9]), "+f"(d[10]), "+f"(d[11]), "+f"(d[12]), "+f"(d[13]), "+f"(d[14]), "+f"(d[15]), "+f"(d[16]), "+f"(d[17]), "+f"(d[18]), "+f"(d[19])
               : "r"(a[0]), "r"(a[1]), "r"(a[2]), "r"(a[3]), "l"(descB), "n"(scale_d));
}
__device__ __forceinline__ void wgmma_copy(float* d, uint32_t da, uint64_t descB) {
  asm volatile("{\n.reg .pred p;\n.reg .b64 a;\nsetp.ne.b32 p, 0, 0;\nmov.b64 a, {%64, 0x40000040};\n"
               "wgmma.mma_async.sync.aligned.m64n16k16.f32.bf16.bf16 {%0,%1,%2,%3,%4,%5,%6,%7}, a, %65, p, 1, 1, 0, 0;\nadd.s64 a, a, 2;\n"
               "wgmma.mma_async.sync.aligned.m64n16k16.f32.bf16.bf16 {%8,%9,%10,%11,%12,%13,%14,%15}, a, %65, p, 1, 1, 0, 0;\nadd.s64 a, a, 2;\n"
               "wgmma.mma_async.sync.aligned.m64n16k16.f32.bf16.bf16 {%16,%17,%18,%19,%20,%21,%22,%23}, a, %65, p, 1, 1, 0, 0;\nadd.s64 a, a, 2;\n"
               "wgmma.mma_async.sync.aligned.m64n16k16.f32.bf16.bf16 {%24,%25,%26,%27,%28,%29,%30,%31}, a, %65, p, 1, 1, 0, 0;\nadd.s64 a, a, 1018;\n"
               "wgmma.mma_async.sync.aligned.m64n16k16.f32.bf16.bf16 {%32,%33,%34,%35,%36,%37,%38,%39}, a, %65, p, 1, 1, 0, 0;\nadd.s64 a, a, 2;\n"
               "wgmma.mma_async.sync.aligned.m64n16k16.f32.bf16.bf16 {%40,%41,%42,%43,%44,%45,%46,%47}, a, %65, p, 1, 1, 0, 0;\nadd.s64 a, a, 2;\n"
               "wgmma.mma_async.sync.aligned.m64n16k16.f32.bf16.bf16 {%48,%49,%50,%51,%52,%53,%54,%55}, a, %65, p, 1, 1, 0, 0;\nadd.s64 a, a, 2;\n"
               "wgmma.mma_async.sync.aligned.m64n16k16.f32.bf16.bf16 {%56,%57,%58,%59,%60,%61,%62,%63}, a, %65, p, 1, 1, 0, 0;\n"
               "}\n"
               : "+f"(d[0]), "+f"(d[1]), "+f"(d[2]), "+f"(d[3]), "+f"(d[4]), "+f"(d[5]), "+f"(d[6]), "+f"(d[7]), "+f"(d[8]), "+f"(d[9]), "+f"(d[10]), "+f"(d[11]), "+f"(d[12]), "+f"(d[13]), "+f"(d[14]), "+f"(d[15]), "+f"(d[16]), "+f"(d[17]), "+f"(d[18]), "+f"(d[19]), "+f"(d[20]), "+f"(d[21]), "+f"(d[22]), "+f"(d[23]), "+f"(d[24]), "+f"(d[25]), "+f"(d[26]), "+f"(d[27]), "+f"(d[28]), "+f"(d[29]), "+f"(d[30]), "+f"(d[31]), "+f"(d[32]), "+f"(d[33]), "+f"(d[34]), "+f"(d[35]), "+f"(d[36]), "+f"(d[37]), "+f"(d[38]), "+f"(d[39]), "+f"(d[40]), "+f"(d[41]), "+f"(d[42]), "+f"(d[43]), "+f"(d[44]), "+f"(d[45]), "+f"(d[46]), "+f"(d[47]), "+f"(d[48]), "+f"(d[49]), "+f"(d[50]), "+f"(d[51]), "+f"(d[52]), "+f"(d[53]), "+f"(d[54]), "+f"(d[55]), "+f"(d[56]), "+f"(d[57]), "+f"(d[58]), "+f"(d[59]), "+f"(d[60]), "+f"(d[61]), "+f"(d[62]), "+f"(d[63])
               : "r"(da), "l"(descB));
}
__device__ __forceinline__ uint64_t make_desc(uint32_t addr, uint32_t lbo_bytes, uint32_t sbo_bytes) {
  return (uint64_t)((addr & 0x3FFFF) >> 4) | ((uint64_t)(lbo_bytes >> 4) << 16) | ((uint64_t)(sbo_bytes >> 4) << 32) | (1ull << 62);
}

__device__ __forceinline__ void ldsm_x4(uint32_t addr, uint32_t& r0, uint32_t& r1, uint32_t& r2, uint32_t& r3) {
  asm volatile("ldmatrix.sync.aligned.m8n8.x4.shared.b16 {%0,%1,%2,%3}, [%4];" : "=r"(r0), "=r"(r1), "=r"(r2), "=r"(r3) : "r"(addr) : "memory");
}
__device__ __forceinline__ void ldsm_x4_t(uint32_t addr, uint32_t& r0, uint32_t& r1, uint32_t& r2, uint32_t& r3) {
  asm volatile("ldmatrix.sync.aligned.m8n8.x4.trans.shared.b16 {%0,%1,%2,%3}, [%4];" : "=r"(r0), "=r"(r1), "=r"(r2), "=r"(r3) : "r"(addr) : "memory");
}
__device__ __forceinline__ void stsm_x4(uint32_t addr, uint32_t r0, uint32_t r1, uint32_t r2, uint32_t r3) {
  asm volatile("stmatrix.sync.aligned.m8n8.x4.shared.b16 [%0], {%1,%2,%3,%4};" :: "r"(addr), "r"(r0), "r"(r1), "r"(r2), "r"(r3) : "memory");
}
__device__ __forceinline__ void stsm_x4_t(uint32_t addr, uint32_t r0, uint32_t r1, uint32_t r2, uint32_t r3) {
  asm volatile("stmatrix.sync.aligned.m8n8.x4.trans.shared.b16 [%0], {%1,%2,%3,%4};" :: "r"(addr), "r"(r0), "r"(r1), "r"(r2), "r"(r3) : "memory");
}
__device__ __forceinline__ void sts128(uint32_t addr, uint32_t a, uint32_t b, uint32_t c, uint32_t d) {
  asm volatile("st.shared.v4.u32 [%0], {%1,%2,%3,%4};" :: "r"(addr), "r"(a), "r"(b), "r"(c), "r"(d) : "memory");
}
__device__ __forceinline__ float lds32f(uint32_t addr) {
  float v;
  asm volatile("ld.shared.f32 %0, [%1];" : "=f"(v) : "r"(addr) : "memory");
  return v;
}
__device__ __forceinline__ void sts32f(uint32_t addr, float a) {
  asm volatile("st.shared.f32 [%0], %1;" :: "r"(addr), "f"(a) : "memory");
}
__device__ __forceinline__ void mma_bf16(float (&c)[4], uint32_t a0, uint32_t a1, uint32_t a2, uint32_t a3, uint32_t b0, uint32_t b1) {
  asm volatile("mma.sync.aligned.m16n8k16.row.col.f32.bf16.bf16.f32 {%0,%1,%2,%3}, {%4,%5,%6,%7}, {%8,%9}, {%0,%1,%2,%3};"
               : "+f"(c[0]), "+f"(c[1]), "+f"(c[2]), "+f"(c[3]) : "r"(a0), "r"(a1), "r"(a2), "r"(a3), "r"(b0), "r"(b1));
}
__device__ __forceinline__ void mma_bf16_z(float (&c)[4], uint32_t a0, uint32_t a1, uint32_t a2, uint32_t a3, uint32_t b0, uint32_t b1) {
  asm volatile("mma.sync.aligned.m16n8k16.row.col.f32.bf16.bf16.f32 {%0,%1,%2,%3}, {%4,%5,%6,%7}, {%8,%9}, {%10,%10,%10,%10};"
               : "=f"(c[0]), "=f"(c[1]), "=f"(c[2]), "=f"(c[3]) : "r"(a0), "r"(a1), "r"(a2), "r"(a3), "r"(b0), "r"(b1), "f"(0.f));
}
__device__ __forceinline__ uint32_t movm_t(uint32_t v) {
  uint32_t r;
  asm volatile("movmatrix.sync.aligned.m8n8.trans.b16 %0, %1;" : "=r"(r) : "r"(v));
  return r;
}
__device__ __forceinline__ uint32_t pack_bf16(float lo, float hi) {
  uint32_t r;
  asm("cvt.rn.bf16x2.f32 %0, %1, %2;" : "=r"(r) : "f"(hi), "f"(lo));
  return r;
}
__device__ __forceinline__ float bf_lo(uint32_t v) { return __uint_as_float(v << 16); }
__device__ __forceinline__ float bf_hi(uint32_t v) { return __uint_as_float(v & 0xFFFF0000u); }
__device__ __forceinline__ void split3(float x, uint32_t& h, uint32_t& m, uint32_t& l) {
  h = pack_bf16(x, 0.f); x -= bf_lo(h);
  m = pack_bf16(x, 0.f); x -= bf_lo(m);
  l = pack_bf16(x, 0.f);
}
__device__ __forceinline__ float ex2(float x) { float r; asm("ex2.approx.ftz.f32 %0, %1;" : "=f"(r) : "f"(x)); return r; }
__device__ __forceinline__ float rcp_fast(float x) { float r; asm("rcp.approx.ftz.f32 %0, %1;" : "=f"(r) : "f"(x)); return r; }
__device__ __forceinline__ void red_v4(float* p, float a, float b, float c, float d) {
  asm volatile("red.global.add.v4.f32 [%0], {%1, %2, %3, %4};" :: "l"(p), "f"(a), "f"(b), "f"(c), "f"(d) : "memory");
}
__device__ __forceinline__ uint4 ld_ll(const uint4* p) {
  uint4 v;
  asm volatile("{\n.reg .b64 a, b;\nld.relaxed.gpu.global.v2.b64 {a, b}, [%4];\nmov.b64 {%0, %1}, a;\nmov.b64 {%2, %3}, b;\n}\n"
               : "=r"(v.x), "=r"(v.y), "=r"(v.z), "=r"(v.w) : "l"(p) : "memory");
  return v;
}
__device__ __forceinline__ void st_b64(uint2* p, uint32_t a, uint32_t b) {
  asm volatile("{\n.reg .b64 v;\nmov.b64 v, {%1, %2};\nst.relaxed.gpu.global.b64 [%0], v;\n}\n" :: "l"(p), "r"(a), "r"(b) : "memory");
}
__device__ __forceinline__ void st_b128(uint4* p, uint32_t a, uint32_t b, uint32_t c, uint32_t d) {
  asm volatile("{\n.reg .b128 v;\nmov.b128 v, {%1, %2, %3, %4};\nst.relaxed.gpu.global.b128 [%0], v;\n}\n" :: "l"(p), "r"(a), "r"(b), "r"(c), "r"(d) : "memory");
}
__device__ __forceinline__ uint4 ld_b128(const uint4* p) {
  uint4 v;
  asm volatile("{\n.reg .b128 v;\nld.relaxed.gpu.global.b128 v, [%4];\nmov.b128 {%0, %1, %2, %3}, v;\n}\n" : "=r"(v.x), "=r"(v.y), "=r"(v.z), "=r"(v.w) : "l"(p) : "memory");
  return v;
}

constexpr float LOG2E = 1.4426950408889634f;

struct Params {
  const __nv_bfloat16* x0;
  const __nv_bfloat16* wA_qkv;
  const __nv_bfloat16* wA_o;
  const __nv_bfloat16* wB_qkv;
  const __nv_bfloat16* wB_phi;
  const __nv_bfloat16* wB_o;
  __nv_bfloat16* out;
};

#define ACC_DEF(d, n) _Pragma("unroll") for (int i_ = 0; i_ < (n); i_++) asm volatile("" : "=f"(d[i_]))
#define ACC_FENCE(d, n) _Pragma("unroll") for (int i_ = 0; i_ < (n); i_++) asm volatile("" : "+f"(d[i_]) :: "memory")
#define PIN(a, n) _Pragma("unroll") for (int i_ = 0; i_ < (n); i_++) asm volatile("" : "+f"((a)[i_]))
#define PINU(a, n) _Pragma("unroll") for (int i_ = 0; i_ < (n); i_++) asm volatile("" : "+r"((a)[i_]))

#define V_ADDR(p0, sw) uint32_t va_[2] = {(p0) + (srowoff >> 1) + (lhi ^ lsw2 ^ (sw)), (p0) + (srowoff >> 1) + ((32 + lhi) ^ lsw2 ^ (sw))}
#define STAGE_V(acc) { \
    _Pragma("unroll") for (int j_ = 0; j_ < 4; j_++) { \
      const float* a_ = (acc) + j_ * 8; \
      stsm_x4(va_[j_ & 1] + (j_ >> 1) * 8192, \
              pack_bf16(rs0 * a_[0], rs0 * a_[1]), pack_bf16(rs1 * a_[2], rs1 * a_[3]), pack_bf16(rs0 * a_[4], rs0 * a_[5]), pack_bf16(rs1 * a_[6], rs1 * a_[7])); } }
#define FRAG(dst, acc, TR, grp) { \
    _Pragma("unroll") for (int i_ = 15; i_ >= 0; i_--) { \
      const float r_ = (i_ & 8) ? rs1 : rs0; \
      const uint32_t w_ = pack_bf16(r_ * (acc)[4 * (i_ & 7) + (i_ >> 3) * 2], r_ * (acc)[4 * (i_ & 7) + (i_ >> 3) * 2 + 1]); \
      (dst)[8 + i_] = (TR) ? movm_t(w_) : w_; \
      if (i_ == 8 && warp >= 6 && mm < 15) { \
        _Pragma("unroll") for (int j_ = 0; j_ < 2; j_++) \
          st_b128(g_halo + (size_t)(mm * 8 + jj) * 512 + ((grp) * 4 + warp * 2 - 12 + j_) * 32 + lane, ((dst)[16 + j_ * 4] & ~1u) | H_BIT(l), (dst)[17 + j_ * 4], (dst)[18 + j_ * 4], (dst)[19 + j_ * 4]); } } \
    PINU((dst) + 8, 16); }
#define FRAG_PUT(src, slot) if (warp < 6) { _Pragma("unroll") for (int j_ = 0; j_ < 2; j_++) \
      sts128(sbase + OFF_S + (slot) * 8192 + 2048 + warp * 1024 + j_ * 512 + lane * 16, (src)[j_ * 4], (src)[j_ * 4 + 1], (src)[j_ * 4 + 2], (src)[j_ * 4 + 3]); }
#define FRAG_GET(dst, slot) { _Pragma("unroll") for (int j_ = 0; j_ < 2; j_++) \
      asm volatile("ld.shared.v4.u32 {%0, %1, %2, %3}, [%4];" : "=r"((dst)[j_ * 4]), "=r"((dst)[j_ * 4 + 1]), "=r"((dst)[j_ * 4 + 2]), "=r"((dst)[j_ * 4 + 3]) \
                   : "r"(sbase + OFF_S + (slot) * 8192 + warp * 1024 + j_ * 512 + lane * 16) : "memory"); }
#define RW(j) (((j) >> 1) * 4 + ((j) & 1))
template <int POS> __device__ __forceinline__ float exps16_(float* o, const float* p) {
  float s[4];
#pragma unroll
  for (int j = 0; j < 16; j++) { o[j] = ex2(POS ? p[RW(j)] : -p[RW(j)]); if (j < 4) s[j] = o[j]; else s[j & 3] += o[j]; }
  const float r = (s[0] + s[1]) + (s[2] + s[3]);
  return r + __shfl_xor_sync(0xffffffffu, r, 1);
}
template <int POS> __device__ __forceinline__ void exps16_fix(float* o, const float* p, float& sum) {
  if (__builtin_expect(__any_sync(0xffffffffu, !(sum > SUMLO && sum < SUMHI)), 0)) {
    float m = p[0], q[32];
#pragma unroll
    for (int j = 1; j < 16; j++) m = POS ? fmaxf(m, p[RW(j)]) : fminf(m, p[RW(j)]);
    const float x = __shfl_xor_sync(0xffffffffu, m, 1);
    m = POS ? fmaxf(m, x) : fminf(m, x);
#pragma unroll
    for (int j = 0; j < 16; j++) q[RW(j)] = p[RW(j)] - m;
    sum = exps16_<POS>(o, q);
  }
}
__device__ __forceinline__ void store16(const float* e, float sum, uint32_t dst, uint32_t dsw, int c0) {
  const float inv = rcp_fast(sum);
#pragma unroll
  for (int j = 0; j < 2; j++)
    sts128(dst + (((c0 + j) << 4) ^ dsw), pack_bf16(e[j * 8] * inv, e[j * 8 + 1] * inv), pack_bf16(e[j * 8 + 2] * inv, e[j * 8 + 3] * inv),
           pack_bf16(e[j * 8 + 4] * inv, e[j * 8 + 5] * inv), pack_bf16(e[j * 8 + 6] * inv, e[j * 8 + 7] * inv));
}
template <int POS> __device__ __forceinline__ void expp16(uint32_t* o, float* p) {
  {
#pragma unroll
    for (int r = 0; r < 4; r += 2) {
      float m = p[r];
#pragma unroll
      for (int j = 1; j < 8; j++) m = POS ? fmaxf(m, p[r + RW(j)]) : fminf(m, p[r + RW(j)]);
#pragma unroll
      for (int s = 1; s <= 2; s <<= 1) { const float x = __shfl_xor_sync(0xffffffffu, m, s); m = POS ? fmaxf(m, x) : fminf(m, x); }
#pragma unroll
      for (int j = 0; j < 8; j++) p[r + RW(j)] -= m;
    }
  }
#pragma unroll
  for (int j = 0; j < 8; j++) o[j] = pack_bf16(ex2(POS ? p[2 * j] : -p[2 * j]), ex2(POS ? p[2 * j + 1] : -p[2 * j + 1]));
}
__device__ __forceinline__ void scale32(float* o, const float* p, float c0, float c1) {
#pragma unroll
  for (int i = 0; i < 32; i++) asm volatile("mul.f32 %0, %1, %2;" : "=f"(o[i]) : "f"(p[i]), "f"((i & 2) ? c1 : c0));
}
__device__ __forceinline__ bool any_big(const float* p) {
  float m[4];
#pragma unroll
  for (int i = 0; i < 32; i++) m[i >> 3] = (i & 7) ? fmaf(p[i], p[i], m[i >> 3]) : p[i] * p[i];
  return __any_sync(0xffffffffu, !(fmaxf(fmaxf(m[0], m[1]), fmaxf(m[2], m[3])) < BIGLIM));
}
__device__ __forceinline__ void phiq_a(float* p, bool big) {
  if (__builtin_expect(!big, 1)) {
#pragma unroll
    for (int j = 0; j < 16; j++) p[j] = ex2(p[j]);
  }
}
template <int NEXT> __device__ __forceinline__ void phiq_b(uint32_t* o, float* p, bool big) {
  if (__builtin_expect(big, 0)) {
    expp16<0>(o, p); expp16<1>(o + 8, p);
  } else {
    if (NEXT) phiq_a(p + 16, false);
#pragma unroll
    for (int j = 0; j < 4; j++) {
      const float a = p[4 * j], b = p[4 * j + 1], c = p[4 * j + 2], d = p[4 * j + 3];
      const float ab = a * b, cd = c * d, r = rcp_fast(ab * cd), x = r * cd, y = r * ab;
      o[2 * j] = pack_bf16(x * b, x * a); o[2 * j + 1] = pack_bf16(y * d, y * c);
      o[8 + 2 * j] = pack_bf16(a, b); o[9 + 2 * j] = pack_bf16(c, d);
    }
  }
}
#define SCHED_FENCE() asm volatile("pmevent 0;" ::: "memory")

__global__ void __cluster_dims__(2, 1, 1) __launch_bounds__(384, 1)
mega_kernel(const __grid_constant__ CUtensorMap tm_x0, const __grid_constant__ CUtensorMap tm_xo, const __grid_constant__ CUtensorMap tm_os,
            const __grid_constant__ CUtensorMap tm_o, const __grid_constant__ CUtensorMap tm_wf,
            const __grid_constant__ CUtensorMap tm_wqA, const __grid_constant__ CUtensorMap tm_wqB,
            const __grid_constant__ CUtensorMap tm_woA, const __grid_constant__ CUtensorMap tm_woB,
            const __grid_constant__ CUtensorMap tm_phi, const Params prm) {
  extern __shared__ __align__(1024) uint8_t smem_raw[];
  const uint32_t sbase = smem_u32(smem_raw);
  const uint32_t bar_full = sbase + OFF_BAR;
  const uint32_t bar_done = bar_full + 384;
  const uint32_t bar_stat = bar_full + 768, bar_stat2 = bar_full + 776, bar_epi = bar_full + 784, bar_phi = bar_full + 936  , bar_halo = bar_full + 904  ;
  const uint32_t bar_xr = bar_full + 800, bar_lx = bar_full + 808, bar_stg = bar_full + 832;
  const uint32_t bar_chk = bar_full + 848;

  const int warp = __shfl_sync(0xffffffffu, threadIdx.x >> 5, 0), lane = threadIdx.x & 31;
  const uint32_t bar_kx = sbase + OFF_ID + 384 + warp * 8;
  uint32_t rank;
  asm volatile("mov.u32 %0, %%cluster_ctarank;" : "=r"(rank));
  const int aux = (int)blockIdx.x - NMAIN, tp = (int)(blockIdx.x >> 1) - 4;
  const int gp = tp < 0 ? 0 : (tp < 32 ? tp & 7 : 1 + (tp - 32) % 7), me = tp < 0 ? tp + 8 : (tp < 32 ? tp >> 3 : 4 + (tp - 32) / 7);
  const int jj = me, cc = gp;
  const int cta = aux >= 0 ? -1 : (cc * 8 + jj) * 2 + (int)rank;
  const int mm = cc * 2 + (int)rank;

#define LOAD_EPOCH() const unsigned epoch = ld_relaxed(&g_flags.epoch.v), ep1 = epoch + 1; (void)epoch
  int budget = 1 << 22;

  if (cta >= 0) {
    if (warp >= 8 && warp < 8 + EARLY && elect_one()) {
      const int u = warp - 8;
      const uint32_t fb = bar_full + u * 8;
      mbar_init(fb, 1);
      asm volatile("fence.mbarrier_init.release.cluster;" ::: "memory");
      fence_proxy_async_smem();
      mbar_expect_tx(fb, QST + SLOT);
      if (u) __nanosleep(STAG2);
      tma_load_t(sbase + OFF_S + u * SLOT, &tm_x0, fb, jj * 128 + u * 64, mm * 128);
#pragma unroll
      for (int i = 0; i < 6; i++) tma_load_2d(sbase + u * QST + i * 4096, &tm_wqA, fb, jj * 128 + (i >> 1) * 1024, jj * 128 + u * 64 + (i & 1) * 32);
      if (u == 0) PROFT(472);
    }
    __syncwarp();
    {
      const int tx = threadIdx.x;
      const __nv_bfloat16* pf = (tx < 128) ? prm.x0 + (size_t)(mm * 128 + tx) * D_MODEL + jj * 128
                                           : prm.wA_qkv + (size_t)(jj * 128 + (tx & 63)) * 3072 + ((tx - 128) >> 6) * 1024 + jj * 128 + rank * 64;
      if (tx < 320) asm volatile("prefetch.global.L2 [%0];" :: "l"(pf));
      else if (tx == 320) prefetch_tmap(&tm_x0);
      else if (tx == 352) prefetch_tmap(&tm_wqA);
      else if (tx == 383) asm volatile("prefetch.global.L2 [%0];" :: "l"(&g_flags.epoch.v));
    }
    if (elect_one()) {
#pragma unroll
      for (int i = 0; i < 4; i++) {
        const int u = warp * 4 + i;
        if (u >= EARLY) mbar_init(bar_full + u * 8, ((u >= 4 && u < 11) || (u > 32 && u != 40)) ? 2 : 1); mbar_init(bar_done + u * 8, 16);
      }
      mbar_init(bar_stat + warp * 16, 0x111111181182ull >> (4 * warp) & 15);
      mbar_init(bar_stat + warp * 16 + 8, 0x111111121811ull >> (4 * warp) & 15);
      mbar_init(bar_chk + 112 + (warp & 7) * 8, 1);
      mbar_init(bar_kx, 1);
      asm volatile("fence.mbarrier_init.release.cluster;" ::: "memory");
    }
    __syncwarp();
    __syncthreads();
    asm volatile("barrier.cluster.arrive.relaxed.aligned;" ::: "memory");
  }

  if (cta < 0) {
    LOAD_EPOCH();
    const uint32_t buf = sbase + warp * SLOT, bar = sbase + OFF_BAR + warp * 16;
    const uint32_t lsw = (lane & 7) << 4, lhi = (lane >> 4) << 4, lrow = (lane & 15) * 128;
    const bool el = elect_one();
    if (el) {
      mbar_init(bar, 1); mbar_init(bar + 8, 1);
      asm volatile("fence.mbarrier_init.release.cluster;" ::: "memory");
    }
#pragma unroll 1
    for (int rd = 0; rd < (NLAYERS > 1 ? 5 : 2); rd++) {
      if (rd >= 2 && warp >= 8) break;
      const int tk = rd < 2 ? aux * 12 + warp : aux * 8 + warp;
      const int half = tk & 1;
      const int blk = rd < 2 ? (tk >> 1) * 2 + rd : (4 - rd) * 16 + (tk >> 1);
      const CUtensorMap* tm = rd < 2 ? &tm_wqA : (rd == 2 ? &tm_wqB : &tm_wf);
      const int j0 = (blk & 15) >> 1;
#define AUX_LOAD(n) { const uint32_t d_ = buf + ((n) & 1) * 8192, b_ = bar + ((n) & 1) * 8; const int r_ = kslice(j0, 2 * (n) + half) * 64; \
        mbar_expect_tx(b_, 8192); tma_load_2d(d_, tm, b_, blk * 64, r_); tma_load_2d(d_ + 4096, tm, b_, blk * 64, r_ + 32); }
      if (el) {
        if (rd == 3) { wait_flag(&g_flags.wfready[j0].v, ep1 * 16); fence_proxy_async_global(); }
        AUX_LOAD(0); AUX_LOAD(1);
      }
      __syncwarp();
      float cs[8][4];
#pragma unroll
      for (int i = 0; i < 8; i++) cs[i][0] = cs[i][1] = cs[i][2] = cs[i][3] = 0.f;
#pragma unroll 1
      for (int n = 0; n < 8; n++) {
        const uint32_t tb = buf + (n & 1) * 8192 + lrow;
        mbar_wait(bar + (n & 1) * 8, (n >> 1) & 1);
#pragma unroll
        for (int i = 0; i < 16; i++) {
          uint32_t b0, b1, b2, b3;
          ldsm_x4_t(tb + (i >> 2) * 2048 + (((i & 3) * 32 + lhi) ^ lsw), b0, b1, b2, b3);
          mma_bf16(cs[2 * (i & 3)], 0x3F803F80u, 0x3F803F80u, 0x3F803F80u, 0x3F803F80u, b0, b1);
          mma_bf16(cs[2 * (i & 3) + 1], 0x3F803F80u, 0x3F803F80u, 0x3F803F80u, 0x3F803F80u, b2, b3);
        }
        __syncwarp();
        if (el && n < 6) AUX_LOAD(n + 2);
        __syncwarp();
      }
      if (lane < 4) {
#pragma unroll
        for (int i = 0; i < 8; i++) st_b64(&g_colsum[rd >= 2][blk * 32 + i * 4 + lane][half], __float_as_uint(cs[i][0]), (__float_as_uint(cs[i][1]) & ~3u) | (ep1 & 3));
      }
      __syncwarp();
    }
  } else if (warp >= 8) {
    asm volatile("setmaxnreg.dec.sync.aligned.u32 40;");
    if (warp == 8) {
      const bool el = elect_one();
      cluster_wait();
      if (el) {
#pragma unroll 1
        for (int l = 0; l < NLAYERS; l++) {
          const uint32_t par = l & 1;
          const CUtensorMap* tqk = par ? &tm_wf : &tm_wqA;
          const CUtensorMap* tv = par ? &tm_wqB : &tm_wqA;
          const CUtensorMap* two = par ? &tm_woB : &tm_woA;
          if (l == 1) { LOAD_EPOCH(); wait_flag(&g_flags.wfready[jj].v, ep1 * 16); fence_proxy_async_global(); }
#pragma unroll 1
          for (int u = l ? 0 : EARLY; u < 32; u++) {
            if (u >= 4) mbar_wait_sl(bar_done + (u - 4) * 8, par);
            else if (l) mbar_wait_sl(bar_done + (43 + u + (u >> 1)) * 8, par ^ 1);
            else mbar_wait_sl(bar_full, 0);
            const uint32_t fb = bar_full + u * 8;
            const bool res = u < 11 || (u >= 18 && u < 22);
            mbar_expect_tx(fb, res ? QST : QST + SLOT);
            const int row = kslice(jj, u < 4 ? u & 1 : (u < 18 ? u - 2 : (u < 22 ? u - 6 : u - 20))) * 64 + (int)rank * 32;
            const int ps = u < 4 ? u >> 1 : (u >= 18), col = jj * 128 + ps * 64;
            const int c0 = par ? jj * 128 + (ps ? 0 : 1024) : col;
            const uint32_t dst = sbase + (u & 3) * QST + rank * 4096;
            tma_load_2d_mc(dst, tqk, fb, c0, row);
            tma_load_2d_mc(dst + 8192, tqk, fb, c0 + (par ? 64 : 1024), row);
            tma_load_2d_mc(dst + 16384, tv, fb, col + 2048, row);
            if (l == PRL && u >= PRU && u < PRU + 4) PROFT(473 + u - PRU);
          }
#pragma unroll 1
          for (int s = 0; s < 16; s++) {
            if (s < 5) { if (s != 2 && s != 4) mbar_wait_sl(bar_done + (28 + s) * 8, par); }
            else if (s != 14) mbar_wait_sl(bar_done + (27 + s - (s == 15)) * 8, par);
            const uint32_t fb = bar_full + (32 + s) * 8;
            mbar_expect_tx(fb, SLOT);
            tma_load_2d_mc(sbase + rank * 8192 + (uint32_t)((WO_BSLOT >> (4 * s)) & 15) * SLOT, two, fb, jj * 128 + (int)rank * 64, wslice(jj, s) * 64);
            const int ts = s + 1;
            if (s >= 5 && ts < 8) {
              mbar_expect_tx(bar_chk - 8 + ts * 8, SLOT);
              tma_load_t(sbase + (uint32_t)((WO_ASLOT(par) >> (4 * ts)) & 15) * SLOT, &tm_o, bar_chk - 8 + ts * 8, wslice(jj, ts) * 64, mm * 128);
            }
          }
        }
      }
      __syncwarp();
    } else if (warp == 9) {
      const bool el = elect_one();
      LOAD_EPOCH();
#pragma unroll 1
      for (int lp = 0; lp < 4 * NLAYERS; lp++) {
        const int l = lp >> 2, ph = lp & 3;
        if (ph == 3) continue;
        const uint32_t par = l & 1;
        const unsigned* pp = reinterpret_cast<const unsigned*>(g_obuf + (ph >> 1) * 64 + (size_t)(mm * 128 + (ph ? 0 : S_LEN) + ((lane & 7) | PROWS) * 16 + (jj & 1) * 8) * D_MODEL +
                                                               (jj >> 1) * 16 + srcb(jj, lane >> 3) * 128);
        const CUtensorMap* tm = lp ? &tm_o : &tm_x0;
        const int row = mm * 128 + ((ph || !l) ? 0 : S_LEN);
        const uint32_t bit = ph ? O_BIT(l) : X_BIT(l - 1);
        const uint32_t slots = ph ? (uint32_t)(WO_ASLOT(par) >> (ph * 32 - 28)) : 0x8769876u;
        const unsigned long long fr = ph == 0 ? XPACE : ph == 1 ? (par ? FRB : 0x35351F1E1Dull) : 0x27262524232232ull;
        uint32_t no = (lp == 0 || (lp & 7) == 1) ? 0 : (ph == 1 ? NOB : (ph ? NO1 : NOX)), v0 = 0, v1 = 0;
        mbar_wait_sl(ph ? bar_done + ((uint32_t)fr & 63) * 8 : (l ? bar_done + 47 * 8 : bar_full), ph ? par : (l ? par ^ 1 : 0));
        if (el && ph) PROFT(324 + l * 16 + ph);
        __syncwarp();
        if (no && (ph == 1 ? SPD1 : (ph ? SPD2 : SPD0))) __nanosleep(ph == 1 ? SPD1 : (ph ? SPD2 : SPD0));
        if (no) { v0 = ld_relaxed(pp); __nanosleep(POLLGAP); v1 = ld_relaxed(pp); }
#pragma unroll 1
        for (int i = 0; i < (ph == 1 ? 5 : 7); i++, no >>= 8) {
#pragma unroll 1
          for (int it = 0; (no & 0xFF) && it < (1 << 18); it++) {
            no &= __ballot_sync(0xffffffffu, (v0 ^ bit) & 1) >> (8 * i);
            if (no) v0 = ld_relaxed(pp);
            if (!(no & 0xFF)) break;
            no &= __ballot_sync(0xffffffffu, (v1 ^ bit) & 1) >> (8 * i);
            if (no) v1 = ld_relaxed(pp);
          }
          if (ph || i >= 4) mbar_wait_sl(bar_done + ((uint32_t)(fr >> (8 * i)) & 63) * 8, par);
          if (el) {
            if (i == 0) PROFT(320 + l * 16 + ph);
            const uint32_t cb = (lp ? bar_chk + (ph >> 1) * 112 : bar_full + 32) + i * 8;
            mbar_expect_tx(cb, SLOT);
            tma_load_t(sbase + ((slots >> (4 * i)) & 15) * SLOT, tm, cb, srcb(jj, i) * 128 + (ph >> 1) * 64, row);
          }
          __syncwarp();
        }
        if (ph == 0 && el) {
          if (l) { wait_flag(&g_flags.xready[l][mm].v, ep1 * 8); fence_proxy_async_global(); }
#pragma unroll 1
          for (int u = 11; u < 34; u++) {
            if (u == 18) u = 22;
            mbar_wait_sl(bar_done + (u - 4) * 8, par);
            if (u == 32) mbar_expect_tx(bar_xr, 2 * SLOT);
            tma_load_t(sbase + OFF_RA + (u & 3) * SLOT, tm, u < 32 ? bar_full + u * 8 : bar_xr, kslice(jj, u < 18 ? u - 2 : (u < 32 ? u - 20 : u - 32)) * 64, row);
          }
        }
        __syncwarp();
      }
      if (el && atomicAdd(&g_flags.done.v, 1) == ep1 * NMAIN - 1) asm volatile("st.relaxed.gpu.global.u32 [%0], %1;" :: "l"(&g_flags.epoch.v), "r"(ep1) : "memory");
      __syncwarp();
      cluster_wait();
    } else {
      const int hw = warp - 10;
      LOAD_EPOCH();
      const bool el = elect_one();
      cluster_wait();
      if (hw == 0) {
        mbar_wait_sl(bar_full + 8, 0);
        if (lane < 7) prefetch_tmap(lane == 0 ? &tm_os : lane == 1 ? &tm_o : lane == 2 ? &tm_wf : lane == 3 ? &tm_wqB : lane == 4 ? &tm_woA : lane == 5 ? &tm_woB : &tm_phi);
#pragma unroll 1
        for (int i = 0; i < (NLAYERS > 1 ? 9 : 0); i++) {
          if (i == 0 || i == 5) mbar_wait_sl(bar_done + (i ? FD1 : FD0) * 8, 0);
          if (el) {
            if (i == 0) { mbar_expect_tx(bar_phi, 2 * SLOT + 8192); tma_load_2d(sbase + OFF_PHI, &tm_phi, bar_phi, 0, jj * 128); }
            else tma_load_2d(sbase + (i > 4 ? 10 : 12) * SLOT - 4096 + i * 4096, &tm_wqB, bar_phi, (i > 4 ? 896 : 0) + jj * 128 + ((i - 1) >> 1) * 64, mm * 64 + (~i & 1) * 32);
          }
          __syncwarp();
          __nanosleep(PFGAP);
        }
      } else {
        if (lane < 24) {
          const uint32_t one = (lane & 8) ? 0u : 0x3F80u << ((lane & 1) * 16), w = (lane >> 1) & 3;
          sts128(sbase + OFF_ID + lane * 16, w == 0 ? one : 0u, w == 1 ? one : 0u, w == 2 ? one : 0u, w == 3 ? one : 0u);
        }
#pragma unroll 1
        for (int b = 0; b < 2; b++) {
          float4* z = reinterpret_cast<float4*>(g_kv[b] + (jj * 4) * KVH + mm * (4 * KVH / 16)) + lane;
#pragma unroll
          for (int i = 0; i < 6; i++) z[i * 32] = make_float4(0.f, 0.f, 0.f, 0.f);
        }
#pragma unroll 1
        for (int i = 0; i < 16; i++) {
          const int b = i >> 2;
          const uint32_t v = (b == 0 ? O_BIT(0) : b == 1 ? X_BIT(0) : H_BIT(0)) + 1;
          uint4* p = b < 2 ? reinterpret_cast<uint4*>(g_obuf + (size_t)(b * S_LEN + mm * 128 + (i & 3) * 32 + (lane >> 3) * 8) * D_MODEL + jj * 128 + (b ? 0 : 64)) + (lane & 7)
                           : g_halo + (size_t)(mm * 8 + jj) * 512 + i * 32 + lane;
          *p = make_uint4(v, v, v, v);
        }
        fence_proxy_async_global();
      }
      __syncwarp();
      uint32_t chkp = 0;
#pragma unroll 1
      for (int lp = hw; lp < 8 * NLAYERS; lp++) {
        const int l = lp >> 3, tk = lp & 7, ph = tk ? 2 - hw : 0;
        const uint32_t par = l & 1;
        int lane; asm volatile("mov.u32 %0, %%laneid;" : "=r"(lane));
        if (tk == 5 || (hw && tk == 0)) {
          const uint32_t bit = ph ? O_BIT(l) : X_BIT(l - 1);
          uint32_t slots = ph ? (uint32_t)(WO_ASLOT(par) >> (ph * 32 - 28)) : 0x8769876u;
          const uint32_t a0 = sbase + (lane & 7) * 126 + lane * 4 + (lane & 1) * 14;
#pragma unroll 1
          for (int c = 0; c < 7; c++, slots >>= 4) {
            const uint32_t cb = bar_chk + 112 - hw * 112 + c * 8;
#pragma unroll 1
            for (int it = 0; it < (1 << 12); it++) {
              mbar_wait_sl(cb, (chkp >> c) & 1);
              chkp ^= 1u << c;
              if (el && c == 0) PROFT(ph == 1 ? 480 + l * 2 : 488 + l * 2 + (ph >> 1));
              uint32_t bad;
              asm volatile("{\n.reg .b32 w<16>;\n"
                           "ld.shared.u32 w0, [%1 + 0];\n"
                           "ld.shared.u32 w1, [%1 + 1024];\n"
                           "ld.shared.u32 w2, [%1 + 2048];\n"
                           "ld.shared.u32 w3, [%1 + 3072];\n"
                           "ld.shared.u32 w4, [%1 + 4096];\n"
                           "ld.shared.u32 w5, [%1 + 5120];\n"
                           "ld.shared.u32 w6, [%1 + 6144];\n"
                           "ld.shared.u32 w7, [%1 + 7168];\n"
                           "ld.shared.u32 w8, [%1 + 8192];\n"
                           "ld.shared.u32 w9, [%1 + 9216];\n"
                           "ld.shared.u32 w10, [%1 + 10240];\n"
                           "ld.shared.u32 w11, [%1 + 11264];\n"
                           "ld.shared.u32 w12, [%1 + 12288];\n"
                           "ld.shared.u32 w13, [%1 + 13312];\n"
                           "ld.shared.u32 w14, [%1 + 14336];\n"
                           "ld.shared.u32 w15, [%1 + 15360];\n"
                           "lop3.b32 w0, w0, w1, %2, 0x7E;\n"
                           "lop3.b32 w2, w2, w3, %2, 0x7E;\n"
                           "lop3.b32 w4, w4, w5, %2, 0x7E;\n"
                           "lop3.b32 w6, w6, w7, %2, 0x7E;\n"
                           "lop3.b32 w8, w8, w9, %2, 0x7E;\n"
                           "lop3.b32 w10, w10, w11, %2, 0x7E;\n"
                           "lop3.b32 w12, w12, w13, %2, 0x7E;\n"
                           "lop3.b32 w14, w14, w15, %2, 0x7E;\n"
                           "lop3.b32 w0, w0, w2, w4, 0xFE;\nlop3.b32 w6, w6, w8, w10, 0xFE;\nlop3.b32 w0, w0, w12, w14, 0xFE;\nlop3.b32 %0, w0, w6, 1, 0xA8;\n}\n"
                           : "=r"(bad) : "r"(a0 + (slots & 15) * SLOT), "r"(bit) : "memory");
              if (__all_sync(0xffffffffu, bad == 0)) break;
              if (el) {
                fence_proxy_async_smem();
                mbar_expect_tx(cb, SLOT);
                tma_load_t(sbase + (slots & 15) * SLOT, &tm_o, cb, srcb(jj, c) * 128 + (ph >> 1) * 64, mm * 128 + (ph ? 0 : S_LEN));
                RETRY_COUNT();
              }
              __syncwarp();
            }
            if (el) { mbar_arrive_local(bar_full + (c + (ph ? 25 + ph * 8 : 4)) * 8); if (lp == PRL * 8 && c == 0) PROFT(477); }
            __syncwarp();
          }
        } else if (hw && (tk & 5) == 1) {
          {
            const int hp = tk >> 1;
            const uint4* src = reinterpret_cast<const uint4*>(g_colsum[par][jj * 64 + hp * 32 + lane]);
            uint32_t bad;
            int it = 0;
            float c[6];
            do {
              bad = 0;
#pragma unroll
              for (int p = 0; p < 3; p++) {
                const uint4 v = ld_ll(src + ((par && p < 2) ? (hp ? -32 : 512) + p * 32 : p * 512));
                bad |= (v.y ^ ep1) | (v.w ^ ep1);
                c[2 * p] = __uint_as_float(v.x) + __uint_as_float(v.z); c[2 * p + 1] = __uint_as_float(v.y) + __uint_as_float(v.w);
              }
              bad &= 3;
              if (bad) __nanosleep(300);
            } while (bad && ++it < (1 << 16));
#pragma unroll
            for (int p = 0; p < 6; p++) {
              uint32_t h, m, lo;
              split3(c[p], h, m, lo);
              sts128(sbase + OFF_LNB + hp * 4096 + (p >> 1) * 1024 + lane * 32 + (p & 1) * 16, h | (m << 16), h | (lo << 16), h | (m << 16), lo | (m << 16));
            }
            fence_proxy_async_smem();
            __syncwarp();
            if (el) { mbar_arrive_local(hp ? bar_stat2 : bar_stat); if (hp == 0) PROFT(324 + l * 16); }
            __syncwarp();
          }
        } else if (tk == 0) {
          mbar_wait_sl(bar_done + 24, par);
          const uint4* sp = reinterpret_cast<const uint4*>(g_stats + (size_t)(mm * 128) * 8) + lane;
#pragma unroll 1
          for (int hf = 0; hf < 4; hf++) {
            uint4 v[4];
            uint32_t bad;
            int it = 0;
            do {
              bad = 0;
#pragma unroll
              for (int i = 0; i < 4; i++) { v[i] = ld_ll(sp + (hf * 4 + i) * 32); bad |= (v[i].y ^ STAT_TAG(l)) | (v[i].w ^ STAT_TAG(l)); }
              bad &= 3;
              if (bad) __nanosleep(200);
            } while (bad && ++it < (1 << 16));
            __syncwarp();
            float mean = 0.f, m2 = 0.f;
#pragma unroll
            for (int i = 0; i < 4; i++) {
              float a = __uint_as_float(v[i].x) + __uint_as_float(v[i].z);
              a += __shfl_xor_sync(0xffffffffu, a, 1); a += __shfl_xor_sync(0xffffffffu, a, 2);
              a *= 0.125f;
              const float e0 = __uint_as_float(v[i].x) - a, e1 = __uint_as_float(v[i].z) - a;
              float q = fmaf(fmaf(e0, e0, e1 * e1), 128.f, __uint_as_float(v[i].y) + __uint_as_float(v[i].w));
              q += __shfl_xor_sync(0xffffffffu, q, 1); q += __shfl_xor_sync(0xffffffffu, q, 2);
              if ((lane & 3) == i) { mean = a; m2 = q; }
            }
            const uint32_t row = hf * 32 + (lane & 3) * 8 + (lane >> 2);
            uint32_t h, m, lo;
            split3(-0.5f * mean, h, m, lo);
            sts128(sbase + OFF_LNA + row * 16, h | (h << 16), m | (h << 16), lo | (m << 16), m | (lo << 16));
            sts32f(sbase + OFF_ST + row * 4, rsqrtf(m2 * (1.f / 1024.f) + 1e-5f));
          }
          fence_proxy_async_smem();
          __syncwarp();
          if (el) { mbar_arrive_local(bar_stat); PROFT(323 + l * 16); }
          __syncwarp();
#pragma unroll 1
          for (int i = 0; i < 8 - 4 * l; i++) {
            asm volatile("prefetch.global.L2 [%0];" :: "l"(i < 4 ? (l ? prm.wB_o : prm.wA_o) + (size_t)cta * 8192 + i * 2048 + lane * 64
                                                                 : prm.wB_qkv + (size_t)(cta * 8 + (i - 4) * 2 + (lane >> 4)) * 3072 + 2048 + (lane & 15) * 64));
            __nanosleep(PFGAP);
          }
        } else if (lp == 3) {
#pragma unroll 1
          for (int c = 0; c < (NLAYERS > 1 ? 8 : 0); c++) {
            if (!(c & 3)) { asm volatile("bar.sync %0, 288;" :: "r"(BAR_WF + (c >> 2)) : "memory"); fence_proxy_async_smem(); }
            if (el) {
              tma_store_2d(&tm_wf, sbase + 11 * SLOT + c * 4096, (c < 4 ? 1024 : -128) + jj * 128 + (c >> 1) * 64, mm * 64 + (c & 1) * 32);
              if (c == 7) {
                asm volatile("cp.async.bulk.commit_group;\ncp.async.bulk.wait_group.read 0;" ::: "memory");
                mbar_arrive_local(bar_phi + 8);
              } else __nanosleep(WFGAP);
            }
            __syncwarp();
          }
          if (el) { bulk_commit_wait(); signal_release(&g_flags.wfready[jj].v); PROFT(335); }
          __syncwarp();
        } else if (tk == 2 || tk == 4) {
          if (par) continue;
          const int i = tk >> 2;
          mbar_wait_sl(bar_done + (i ? HW1 : (hw ? 19 : HW0)) * 8, 0);
          const uint4* src = g_halo + (size_t)(mm * 8 + jj - 8) * 512 + i * 256 + hw * 128 + lane;
          uint4 v[4];
          int it = 0;
          bool ok;
          do {
#pragma unroll
            for (int j = 0; j < 4; j++) v[j] = mm ? ld_b128(src + j * 32) : make_uint4(H_BIT(l), 0, 0, 0);
            ok = __all_sync(0xffffffffu, (((v[0].x ^ H_BIT(l)) | (v[1].x ^ H_BIT(l)) | (v[2].x ^ H_BIT(l)) | (v[3].x ^ H_BIT(l))) & 1) == 0);
          } while (!ok && ++it < (1 << 16));
#pragma unroll
          for (int j = 0; j < 4; j++) sts128(sbase + OFF_S + hw * 8192 + j * 512 + lane * 16, v[j].x, v[j].y, v[j].z, v[j].w);
          __syncwarp();
          if (el) { mbar_arrive_local(bar_halo + hw * 8); PROFT(331 + l * 16 + i * 2 + hw); }
          __syncwarp();
        } else if (tk == 6 && hw == 0 && l < NLAYERS - 1) {
          bar_sync<BAR_X1, 288>();
          if (el) {
            PROFT(328 + l * 16);
            mbar_wait_sl(bar_full + XD * 8, par ^ 1);
            tma_store_t(&tm_o, sbase + 11 * SLOT, jj * 128 + 64, mm * 128 + S_LEN);
            bulk_commit_wait();
            signal_release(&g_flags.xready[l + 1][mm].v);
            PROFT(330 + l * 16);
          }
          __syncwarp();
        }
      }
    }
    cluster_sync();
  } else {
    asm volatile("setmaxnreg.inc.sync.aligned.u32 232;");
    const int wg = warp >> 2;
    const int r0 = warp * 16;
    const uint32_t pK = sbase + OFF_S, pV = sbase + OFF_S + SLOT;
#define PMASKS(on, bit) const uint32_t pm0 = ((on) && t == (g >> 1)), pbit = (bit)
#define PBIT(w) (((w) & ~pm0) | (pbit & pm0))
#define LANE_CONSTS() \
    int lane; asm volatile("mov.u32 %0, %%laneid;" : "=r"(lane)); \
    const int g = lane >> 2, t = lane & 3; \
    const uint32_t srowoff = (r0 + (lane & 15)) * 128, lsw = (lane & 7) << 4, lhi = (lane >> 4) << 4, lsw2 = (lane & 6) << 3; \
    (void)g; (void)t; (void)srowoff; (void)lsw; (void)lhi; (void)lsw2;
    uint32_t stgp = 0, peer;
    asm volatile("mapa.shared::cluster.u32 %0, %1, %2;" : "=r"(peer) : "r"(sbase), "r"(rank ^ 1));
    peer -= sbase;
    const uint32_t dA0 = (((sbase & 0x3FFFF) + wg * 8192) >> 4) | 0x10000u, dB0 = ((sbase & 0x3FFFF) >> 4) | 0x2000000u;
    cluster_wait();
#define DESC(lo, hi) ((uint64_t)(uint32_t)(lo) | ((uint64_t)(hi) << 32))
#define STG_ARRIVE() { __syncwarp(); if (elect_one()) mbar_arrive_local(bar_stg); }
#define STG_WAIT() { mbar_wait(bar_stg, stgp); stgp ^= 1; }
#define PROFS() do {} while (0)
#define REL(addr) { if (elect_one()) { mbar_arrive_local(addr); asm volatile("mbarrier.arrive.shared::cluster.b64 _, [%0];" :: "r"((addr) + peer) : "memory"); } }
#define QSTEP(ACC, DA, SC) { \
      const uint32_t da = (DA), db = dB0 + (ub & 0x18) * (QST >> 7); \
      mbar_wait(ub, par); \
      wgmma_fence(); \
      wgmma4_n192<SC>(ACC, da, db); \
      wgmma_commit(); PROFS(); }
#define QREL() { wgmma_wait<1>(); REL(ub + 376); ub += 8; }
#define RA_CUR (dA0 + (OFF_RA >> 4) + (ub & 0x18) * (SLOT >> 7))
#define PUMP1() { QSTEP(S1, RA_CUR, 1); QREL(); }
#define PUMPN() { wgmma_fence(); wgmma4_n192<1>(S1, RA_CUR, dB0 + (ub & 0x18) * (QST >> 7)); wgmma_commit(); PROFS(); QREL(); }
#define PUMP0() { PUMP1(); SCHED_FENCE(); }
#define WSTEP() { \
      const uint32_t s4 = (ub - bar_full - 256) >> 1; \
      const uint32_t da = dA0 + (((uint32_t)(WO_ASLOT(par) >> s4) & 15) << 10), db = dB0 + (((uint32_t)(WO_BSLOT >> s4) & 15) << 10); \
      mbar_wait(ub, par); \
      wgmma_fence(); \
      wgmma4_n128<1>(S1, da, db); \
      wgmma_commit(); PROFS(); \
      wgmma_wait<1>(); \
      if (s4) REL(ub + 376); \
      ub += 8; }
#define PUMPS(n) { _Pragma("unroll 1") for (int i_ = 0; i_ < (n); i_++) PUMP1(); }
#define LNSTEP(ACC, hh) { wgmma_fence(); wgmma_n192<1, 0>(ACC, make_desc(sbase + OFF_LNA + wg * 1024, 0, 128) ^ (1ull << 62), make_desc(sbase + OFF_LNB + (hh) * 4096, 0, 128) ^ (1ull << 62)); }
#define WARP_STORE(tm, tile, col, row) { fence_proxy_async_smem(); __syncwarp(); WARP_STORE0(tm, tile, col, row); }
#define WARP_STORE0(tm, tile, col, row) { \
      if (elect_one()) { tma_store_2d(tm, (tile) + r0 * 128, col, (row) + r0); asm volatile("cp.async.bulk.commit_group;" ::: "memory"); } __syncwarp(); }
#define TILE_CONSTS(base, on, bit) \
      uint32_t ta[5]; \
      { PMASKS(on, bit); (void)pbit; ta[4] = pm0; } \
      _Pragma("unroll") for (int j = 0; j < 4; j++) ta[j] = (base) + srowoff + ((((uint32_t)j << 5) + lhi) ^ lsw); \
      PINU(ta, 5); SCHED_FENCE(); \
      const uint32_t pm0 = ta[4], pbit = (bit)
#define X_OUT(pc, W) { \
      _Pragma("unroll") for (int j = 0; j < 4; j++) \
        stsm_x4(ta[j] + (pc) * SLOT, \
                PBIT(pack_bf16((W)[j * 8 + 0], (W)[j * 8 + 1])), PBIT(pack_bf16((W)[j * 8 + 2], (W)[j * 8 + 3])), \
                (pack_bf16((W)[j * 8 + 4], (W)[j * 8 + 5])), (pack_bf16((W)[j * 8 + 6], (W)[j * 8 + 7]))); }
#define REST_P1(SKEW) { \
      mbar_wait(bar_stat2, par); \
      LNSTEP(S1, 1); \
      wgmma_commit(); \
      _Pragma("unroll 1") while (ub < bar_full + 256) { \
        const bool hold = ub == bar_full + 256 - 8 * (SKEW) && wg == 0; \
        if (hold) { wgmma_wait<0>(); REL(ub + 376); bar_sync<BAR_SKEW, 256>(); } \
        QSTEP(S1, RA_CUR, 1); \
        if (ub == bar_full + 248 && wg == 1) bar_arrive<BAR_SKEW, 256>(); \
        wgmma_wait<1>(); if (!hold) REL(ub + 376); ub += 8; \
      } \
      mbar_wait(bar_done + (31 - (SKEW)) * 8, par);        \
      wgmma_wait<0>(); \
      ACC_FENCE(S1, 96); \
      REL(bar_done + 31 * 8); \
      PROF(13); }
#define FOLD(tile, rd) { \
          LANE_CONSTS(); \
          float d[32]; \
          ACC_DEF(d, 32); \
          mbar_wait(bar_phi, 0); \
          wgmma_fence(); \
          _Pragma("unroll") for (int i = 0; i < 2; i++) { \
            const uint64_t da = make_desc((tile) + wg * 8192 + i * 64, 16, 1024); \
            const uint64_t db = make_desc(sbase + OFF_PHI + wg * 4096 + i * 2048, 16, 512) ^ (3ull << 62); \
            wgmma_n32<0>(d + i * 16, da, db); wgmma_n32<1>(d + i * 16, da + 2, db + 64); \
          } \
          wgmma_commit(); \
          PUMP0(); \
          ACC_FENCE(d, 32); \
          bar_wg(wg); \
          _Pragma("unroll") for (int i = 0; i < 4; i++) { \
            const float* x = d + (i & 1) * 8 + (i >> 1) * 2; \
            if (rd) sts128((tile) + wg * 8192 + ((warp & 3) * 16 + (i >> 1) * 8 + g) * 128 + (((2 * t + (i & 1)) ^ g) << 4), \
                           pack_bf16(x[0], x[1]), pack_bf16(x[4], x[5]), pack_bf16(x[16], x[17]), pack_bf16(x[20], x[21])); \
            else stsm_x4((tile) + srowoff + ((((uint32_t)i << 5) + lhi) ^ lsw), pack_bf16(d[i * 8], d[i * 8 + 1]), pack_bf16(d[i * 8 + 2], d[i * 8 + 3]), \
                         pack_bf16(d[i * 8 + 4], d[i * 8 + 5]), pack_bf16(d[i * 8 + 6], d[i * 8 + 7])); \
          } \
          }
#define XM_ISSUE() { mbar_wait(bar_xr, par); wgmma_fence(); \
      wgmma_copy(T_, dA0 + (OFF_RA >> 4), make_desc(sbase + OFF_ID, 128, 128) ^ (1ull << 62)); }
#define COPYN(d, s, n) _Pragma("unroll") for (int i_ = 0; i_ < (n); i_++) { uint32_t c_; asm volatile("mov.b32 %0, %1;" : "=r"(c_) : "f"((s)[i_])); (d)[i_] = __uint_as_float(c_); }
#define COPY64(d, s) COPYN(d, s, 64)
#define XM_DONE() { ACC_FENCE(T_, 64); COPY64(S1, T_); ACC_FENCE(S1, 64); \
      __syncwarp(); if (elect_one()) mbar_arrive_local(bar_lx); }
#define LOAD_X() { float T_[64]; ACC_DEF(T_, 64); wgmma_wait<0>(); XM_ISSUE(); wgmma_commit(); wgmma_wait<0>(); XM_DONE(); }

    float S0[96], S1[96];
#define FIRST_STEP(l_) { const int ln_ = (l_), l = ln_; const uint32_t ub = bar_full; (void)l; (void)ub; ACC_DEF(S0, 96); wgmma_fence(); wgmma4_n192<0>(S0, dA0 + (OFF_S >> 4), dB0); wgmma_commit(); PROFS(); }
    LOAD_EPOCH();
    mbar_wait(bar_full, 0);
    FIRST_STEP(0);
#pragma unroll 1
    for (int l = 0;; l++) {
      const uint32_t par = l & 1;
      uint32_t ub = bar_full + 8;
      PROF(1);
      {
        LANE_CONSTS();
        uint32_t ta[4];
#pragma unroll
        for (int j = 0; j < 4; j++) ta[j] = pK + srowoff + ((((uint32_t)j << 5) + lhi) ^ lsw);
        float p0, p1, a0 = 0.f, a1 = 0.f, q0 = 0.f, q1 = 0.f;
#define STATS(j0, j1) _Pragma("unroll") for (int j = (j0); j < (j1); j++) { \
          uint32_t x[4]; \
          ldsm_x4(ta[j & 3] + (j >> 2) * SLOT, x[0], x[1], x[2], x[3]); \
          if (j == 0) { p0 = __shfl_sync(0xffffffffu, bf_lo(x[0]), lane & 28); p1 = __shfl_sync(0xffffffffu, bf_lo(x[1]), lane & 28); } \
          _Pragma("unroll") for (int i = 0; i < 4; i += 2) { \
            const float d0 = bf_lo(x[i]) - p0, d1 = bf_hi(x[i]) - p0, d2 = bf_lo(x[i + 1]) - p1, d3 = bf_hi(x[i + 1]) - p1; \
            a0 += d0 + d1; a1 += d2 + d3; \
            q0 = fmaf(d1, d1, fmaf(d0, d0, q0)); q1 = fmaf(d3, d3, fmaf(d2, d2, q1)); } } \
          asm volatile("" : "+f"(a0), "+f"(a1), "+f"(q0), "+f"(q1), "+f"(p0), "+f"(p1)); SCHED_FENCE()
        if (SB0) { STATS(0, SB0); }
        bar_wg(wg);
        QSTEP(S0, dA0 + ((OFF_S + SLOT) >> 4), 1);
        QREL();
        SCHED_FENCE();
        STATS(SB0, SB1);
        ACC_DEF(S1, 96);
        QSTEP(S1, dA0 + (OFF_S >> 4), 0);
        QREL();
        SCHED_FENCE();
        STATS(SB1, SB2);
        QSTEP(S1, dA0 + ((OFF_S + SLOT) >> 4), 1);
        QREL();
        SCHED_FENCE();
        STATS(SB2, 8);
#pragma unroll
        for (int o = 1; o <= 2; o <<= 1) {
          a0 += __shfl_xor_sync(0xffffffffu, a0, o); a1 += __shfl_xor_sync(0xffffffffu, a1, o);
          q0 += __shfl_xor_sync(0xffffffffu, q0, o); q1 += __shfl_xor_sync(0xffffffffu, q1, o);
        }
        if (t == 1) { a0 = a1; q0 = q1; p0 = p1; }
        if (t < 2) st_b64(g_stats + (size_t)(mm * 128 + r0 + g + t * 8) * 8 + jj, __float_as_uint(fmaf(a0, 1.f / 128.f, p0)),
                          (__float_as_uint(fmaxf(fmaf(a0 * (-1.f / 128.f), a0, q0), 0.f)) & ~3u) | STAT_TAG(l));
        if (l) { asm volatile("cp.async.bulk.wait_group 0;" ::: "memory"); bar_arrive<BAR_X1, 288>(); }
#pragma unroll 1
        for (int i = 0; i < 14; i++) {
          QSTEP(S0, RA_CUR, 1);
          if (i == 0) PROF(2);
          QREL();
        }
      }
      LANE_CONSTS();
      mbar_wait(bar_stat, par);
      LNSTEP(S0, 0);
      wgmma_commit();
      const float rs0 = lds32f(sbase + OFF_ST + (r0 + g) * 4), rs1 = lds32f(sbase + OFF_ST + (r0 + g + 8) * 4);
      PUMP0();
      ACC_FENCE(S0, 96);
      PROF(3);
      if (!par) {
        constexpr uint32_t par = 0;
        uint32_t qa[16];
        uint32_t kf[24], vf[24];
#define DRAIN_A(ACC, hp, PMP) { \
          LANE_CONSTS(); \
          FRAG(kf, ACC + 32, 0, (hp) * 2); \
          PMP; \
          FRAG(vf, ACC + 64, 1, (hp) * 2 + 1); \
          _Pragma("unroll") for (int i_ = 0; i_ < 16; i_++) qa[i_] = pack_bf16(ACC[2 * i_], ACC[2 * i_ + 1]); \
          PINU(qa, 16); }
        DRAIN_A(S0, 0, PUMP0());
        if (l == 0 && NLAYERS > 1) {
#pragma unroll 1
          for (int rd = 1; rd >= 0; rd--) {
            FOLD(sbase + (12 - rd) * SLOT, rd);
            asm volatile("bar.arrive %0, 288;" :: "r"(BAR_WF + 1 - rd) : "memory");
          }
        }
        PUMPS(FPUMP);
#pragma unroll 1
        for (int h = 0; h < 2; h++) {
          PROFH(4, 16);
          LANE_CONSTS();
          FRAG_PUT(kf + 16, 0); FRAG_PUT(vf + 16, 1);
          STG_ARRIVE();
          if (h) { PROF(8); LOAD_X(); PROF(9); WSTEP(); PROF(10); } else PUMPS(HPUMP2);
          const bool gt0 = 2 * t > g, gt1 = 2 * t >= g;
          uint32_t msk[2] = {(gt0 ? 0xFFFFu : 0u) | (gt1 ? 0xFFFF0000u : 0u), g == 2 * t ? 0x10001u : 0u};
          PINU(msk, 2);
          TILE_CONSTS(sbase, false, 0);
          (void)pm0; (void)pbit;
          if (h) PROF(12);
          STG_WAIT();
          if (h) PROF(14);
          if (warp < 2) mbar_wait(bar_halo, h);
          if (h) PROF(15);
          if (h == 0) mbar_wait(ub, par);
          FRAG_GET(kf, 0);
          PROFH(5, 17);
          float s[2][3][4];
#pragma unroll
          for (int ks = 0; ks < 2; ks++)
#pragma unroll
            for (int i = 0; i < 6; i++) {
              const int hh = i & 1, jb = 2 - (i >> 1);
              const uint32_t* b = kf + jb * 8 + hh * 4 + ks * 2;
              if (ks) mma_bf16(s[hh][jb], qa[hh * 8 + 4], qa[hh * 8 + 5], qa[hh * 8 + 6], qa[hh * 8 + 7], b[0], b[1]);
              else mma_bf16_z(s[hh][jb], qa[hh * 8], qa[hh * 8 + 1], qa[hh * 8 + 2], qa[hh * 8 + 3], b[0], b[1]);
            }
          if (h == 0) PUMPN()
          PROFH(6, 18);
          float va[2][2], vb[2][2], mx[2][2];
#pragma unroll
          for (int hh = 0; hh < 2; hh++) {
            va[hh][0] = gt0 ? s[hh][0][0] : s[hh][1][0];
            vb[hh][0] = gt1 ? s[hh][0][1] : s[hh][1][1];
            va[hh][1] = gt0 ? s[hh][1][2] : s[hh][2][2];
            vb[hh][1] = gt1 ? s[hh][1][3] : s[hh][2][3];
          }
          if (warp < 2 && mm == 0) {
#pragma unroll
            for (int hh = 0; hh < 2; hh++) { if (gt0) va[hh][0] = -INFINITY; if (gt1) vb[hh][0] = -INFINITY; }
          }
#pragma unroll
          for (int i = 0; i < 4; i++) mx[i >> 1][i & 1] = fmaxf(va[i >> 1][i & 1], vb[i >> 1][i & 1]);
#pragma unroll
          for (int o = 1; o <= 2; o <<= 1)
#pragma unroll
            for (int i = 0; i < 4; i++) mx[i >> 1][i & 1] = fmaxf(mx[i >> 1][i & 1], __shfl_xor_sync(0xffffffffu, mx[i >> 1][i & 1], o));
          const float sc0 = rs0 * (0.17677669529663687f * LOG2E), sc1 = rs1 * (0.17677669529663687f * LOG2E);
#pragma unroll
          for (int i = 0; i < 4; i++) {
            const float sc = (i & 1) ? sc1 : sc0, m = mx[i >> 1][i & 1];
            va[i >> 1][i & 1] = ex2((va[i >> 1][i & 1] - m) * sc); vb[i >> 1][i & 1] = ex2((vb[i >> 1][i & 1] - m) * sc);
            mx[i >> 1][i & 1] = va[i >> 1][i & 1] + vb[i >> 1][i & 1];
          }
          if (h == 0) { PIN(&va[0][0], 4); PIN(&vb[0][0], 4); PIN(&mx[0][0], 4); PUMP1(); }
          if (h) PROF(20);
          if (warp < 2) mbar_wait(bar_halo + 8, h);
          if (h) PROF(21);
          if (h == 0) mbar_wait(ub, par);
          FRAG_GET(vf, 1);
#pragma unroll
          for (int o = 1; o <= 2; o <<= 1)
#pragma unroll
            for (int i = 0; i < 4; i++) mx[i >> 1][i & 1] += __shfl_xor_sync(0xffffffffu, mx[i >> 1][i & 1], o);
          float o[8][4];
          uint32_t pa[4][2];
#pragma unroll
          for (int i = 0; i < 4; i++) {
            const float iv = rcp_fast(mx[i >> 1][i & 1]);
            const uint32_t w = pack_bf16(va[i >> 1][i & 1] * iv, vb[i >> 1][i & 1] * iv);
            pa[i][0] = w & msk[0]; pa[i][1] = w & ~msk[0];
          }
          PROFH(7, 19);
#pragma unroll
          for (int i = 7; i >= 0; i--) {
            const uint32_t* a = vf + (i >> 2) * 8 + (i & 3) * 2;
            mma_bf16_z(o[i], a[0], a[1], a[8], a[9], pa[(i & 2) + (i >> 2)][0], pa[(i & 2) + (i >> 2)][1]);
          }
          if (h == 0) PUMPN() else mbar_wait(bar_done + 30 * 8, par);
          if (NLAYERS > 1 && l + h == 0) mbar_wait(bar_phi + 8, 0);
          if (h) PROF(22);
          {
            const uint32_t pm0 = msk[1], pbit = O_BIT(l) * 0x10001u;
#pragma unroll
            for (int i = 0; i < 4; i++)
              stsm_x4_t(ta[i] + (h ? 3 : 12) * SLOT, PBIT(pack_bf16(o[i][0], o[i][1])), PBIT(pack_bf16(o[i + 4][0], o[i + 4][1])),
                        pack_bf16(o[i][2], o[i][3]), pack_bf16(o[i + 4][2], o[i + 4][3]));
          }
          WARP_STORE(&tm_os, sbase + (h ? 3 : 12) * SLOT, jj * 128 + h * 64, mm * 128);
          PROFH(11, 23);
          if (h) break;
          REST_P1(ASKEW);
          asm volatile("cp.async.bulk.wait_group.read 0;" ::: "memory");
          DRAIN_A(S1, 1, {});
        }
      } else {
        constexpr uint32_t par = 1;
        float st[32];
        const float c0 = rs0 * LOG2E, c1 = rs1 * LOG2E;
        { V_ADDR(pV, 0); STAGE_V(S0 + 64); }
        if (warp < 2) sts128(sbase + OFF_ONES + warp * 512 + lane * 16, 0x3F803F80u, 0x3F803F80u, 0x3F803F80u, 0x3F803F80u);
        scale32(st, S0, c0, c1);
        PIN(st, 32);
#define PHI_PIECE(c) { \
          e_[2 * (c)] = ex2(st[2 * (c)]); e_[2 * (c) + 1] = ex2(st[2 * (c) + 1]); \
          _Pragma("unroll") for (int k_ = 4 * (c); k_ < 4 * (c) + 4; k_++) m_[(c) >> 1] = (k_ & 7) ? fmaf(st[k_], st[k_], m_[(c) >> 1]) : st[k_] * st[k_]; \
          asm volatile("" : "+f"(e_[2 * (c)]), "+f"(e_[2 * (c) + 1]), "+f"(m_[(c) >> 1])); SCHED_FENCE(); }
#define PHI_FIN() { \
          big = __any_sync(0xffffffffu, !(fmaxf(fmaxf(m_[0], m_[1]), fmaxf(m_[2], m_[3])) < BIGLIM)); \
          if (__builtin_expect(big, 0)) { COPYN(e_, st, 16); } \
          _Pragma("unroll") for (int k_ = 0; k_ < 16; k_++) st[k_] = e_[k_]; \
          PIN(st, 16); }
#define KV_MMA(vs, IL) { \
          const uint32_t dp = dA0 + 12 * 1024 - wg * 2560, dv = dA0 + (vs) * 1024 + ((OFF_ONES - (vs) * SLOT - 16) << 12) - wg * (512 << 16); \
          STG_WAIT(); \
          fence_proxy_async_smem(); \
          wgmma_fence(); \
          _Pragma("unroll") for (int ks = 0; ks < 8; ks++) { \
            const uint64_t a = DESC(dp + ks * 128, 0x40000040), b = DESC(dv + ks * (64 - (64 << 16)), 0x80000020); \
            if ((IL) && ks) wgmma_fence(); \
            if (ks == 0) wgmma_n40<0, 1>(kv, a, b); else wgmma_n40<1, 1>(kv, a, b); \
            if (ks == 7) wgmma_commit(); \
            if (IL) PHI_PIECE(ks); } }
#define KV_RED1(i) if (h) red_v4(g_kv[l >> 1] + (jj * 4) * KVH + warp * 768 + lane * 4 + (i) * 128, S0[32 + (i) * 3], S0[33 + (i) * 3], S0[34 + (i) * 3], 1.f)
#define KV_REDS(n) { _Pragma("unroll") for (int i_ = 0; i_ < 6; i_++) if (((RPACE >> (4 * i_)) & 15) == (n)) KV_RED1(i_); }
#define KV_SEND(kp) { \
          float sd[9]; \
          _Pragma("unroll") for (int i = 0; i < 8; i++) { (kp)[i] = kv[i]; sd[i] = kv[8 + i]; } \
          (kp)[8] = rank ? kv[18] : kv[16]; sd[8] = rank ? kv[16] : kv[18]; \
          const uint32_t ra = sbase + peer + (warp * 32 + lane) * 4, rb = bar_kx + peer; \
          if (elect_one()) mbar_expect_tx(bar_kx, 1152); \
          _Pragma("unroll") for (int i = 0; i < 2; i++) \
            asm volatile("st.async.weak.shared::cluster.mbarrier::complete_tx::bytes.v4.f32 [%0], {%1, %2, %3, %4}, [%5];" \
                         :: "r"(ra + (warp * 32 + lane) * 12 + OFF_PHI + i * 4096), "f"(sd[4 * i]), "f"(sd[4 * i + 1]), "f"(sd[4 * i + 2]), "f"(sd[4 * i + 3]), "r"(rb) : "memory"); \
          asm volatile("st.async.weak.shared::cluster.mbarrier::complete_tx::bytes.f32 [%0], %1, [%2];" :: "r"(ra + OFF_LNB), "f"(sd[8]), "r"(rb) : "memory"); }
#define KV_RECV(kp, hp) { \
          float r_[9]; \
          float* kvg = g_kv[l >> 1] + (jj * 4 + (hp) * 2) * KVH + warp * 768 + rank * 384 + lane * 4; \
          mbar_wait(bar_kx, l >> 1); \
          _Pragma("unroll") for (int i = 0; i < 2; i++) \
            asm volatile("ld.shared.v4.f32 {%0, %1, %2, %3}, [%4];" : "=f"(r_[4 * i]), "=f"(r_[4 * i + 1]), "=f"(r_[4 * i + 2]), "=f"(r_[4 * i + 3]) \
                         : "r"(sbase + OFF_PHI + i * 4096 + (warp * 32 + lane) * 16) : "memory"); \
          r_[8] = lds32f(sbase + OFF_LNB + (warp * 32 + lane) * 4); \
          _Pragma("unroll") for (int i = 0; i < 3; i++) red_v4(kvg + i * 128, (kp)[3 * i] + r_[3 * i], (kp)[3 * i + 1] + r_[3 * i + 1], (kp)[3 * i + 2] + r_[3 * i + 2], 2.f); }
#define KV_LOAD(hp) { \
          const uint4* kvg = reinterpret_cast<const uint4*>(g_kv[l >> 1] + (jj * 4 + (hp) * 2) * KVH) + warp * 192 + lane; \
          _Pragma("unroll") for (int i = 0; i < 6; i++) v[i] = ld_b128(kvg + i * 32); }
#define KVV(i) __uint_as_float((i) % 3 == 0 ? v[(i) / 3].x : ((i) % 3 == 1 ? v[(i) / 3].y : v[(i) / 3].z))
#define KV_TILE(hp) { \
          _Pragma("unroll 1") for (int it = 0; it < (1 << 16); it++) { \
            if (__all_sync(0xffffffffu, (v[0].w & v[1].w & v[2].w & v[3].w & v[4].w & v[5].w) == 0x41800000u)) break; \
            RETRY_COUNT(); \
            KV_LOAD(hp); \
          } \
          if (hp) PROF(26); else PROF(25); \
          const uint32_t e = lane & 7, jt = ((lane >> 1) & 4) + (e >> 1); \
          const uint32_t row = ((((warp >> 1) ^ wg) & 1) << 5) + ((jt & 1) << 4) + ((warp & 1) << 3) + (jt & 6) + (e & 1); \
          const uint32_t kd = pV + wg * 8192 + row * 128, ksw = (row & 7) << 4; \
          _Pragma("unroll") for (int i = 0; i < 2; i++) \
            stsm_x4(kd + ((i * 32 + lhi) ^ ksw), pack_bf16(KVV(i * 9), KVV(i * 9 + 1)), pack_bf16(KVV(i * 9 + 2), KVV(i * 9 + 3)), \
                    pack_bf16(KVV(i * 9 + 4), KVV(i * 9 + 5)), pack_bf16(KVV(i * 9 + 6), KVV(i * 9 + 7))); \
          stsm_x4(kd + ((64u + lhi) ^ ksw), pack_bf16(KVV(8), 1.f), pack_bf16(KVV(17), 1.f), 0u, 0u); }
#pragma unroll 1
        for (int h = 0; h < 2; h++) {
          PROFH(4, 6);
          PUMP0();
          LANE_CONSTS();
          const uint32_t dsw = (uint32_t)(g ^ (2 * t)) << 4, dst = ((t & 2) ? pK : sbase + 12 * SLOT) + (r0 + g) * 128;
          float e[16], f[16];
          KV_REDS(1);
          float sa = exps16_<0>(e, st);
          exps16_fix<0>(e, st, sa);
          asm volatile("" : "+f"(sa)); PIN(e, 16); PUMP0();
          if (h) STG_WAIT();
          KV_REDS(2);
          store16(e, sa, dst, dsw, 4);
          float sb = exps16_<1>(f, st);
          exps16_fix<1>(f, st, sb);
          asm volatile("" : "+f"(sb)); PIN(f, 16); PUMP0();
          KV_REDS(3);
          store16(f, sb, dst, dsw, 0);
          float sc = exps16_<0>(e, st + 2);
          exps16_fix<0>(e, st + 2, sc);
          asm volatile("" : "+f"(sc)); PIN(e, 16); PUMP0();
          KV_REDS(4);
          store16(e, sc, dst + 1024, dsw, 4);
          float sd = exps16_<1>(f, st + 2);
          exps16_fix<1>(f, st + 2, sd);
          asm volatile("" : "+f"(sd)); PIN(f, 16); PUMP0();
          store16(f, sd, dst + 1024, dsw, 0);
          PROFH(5, 7);
          if (h) break;
          {
            float kv[20];
            ACC_DEF(kv, 20);
            STG_ARRIVE();
            float e_[16], m_[4];
            KV_MMA(11, 0);
            PUMP0();
            ACC_FENCE(kv, 20);
            STG_ARRIVE();
            scale32(st, S0 + 32, c0, c1);
            PIN(st, 32);
            {
              COPYN(S0 + 32, kv, 8); COPYN(S0 + 40, kv + 16, 1); COPYN(S0 + 41, kv + 8, 8); COPYN(S0 + 49, kv + 18, 1);
              const int h = 1;
              KV_REDS(0);
            }
          }
        }
        bool big;
        uint4 v[6];
        {
          float kv[20];
          { LANE_CONSTS(); KV_LOAD(0); }
          mbar_wait(bar_stat2, par);
          ub = bar_full + 240;
          LNSTEP(S1, 1);
          PUMP1();
          if (wg == 0) bar_sync<BAR_SKEW, 256>();
          QSTEP(S1, RA_CUR, 1);
          if (wg == 1) bar_arrive<BAR_SKEW, 256>();
          QREL();
          { LANE_CONSTS(); KV_TILE(0); }
          LANE_CONSTS();
          V_ADDR(sbase + 3 * SLOT, rank * 32);
          PINU(va_, 2);
          mbar_wait(bar_done + 30 * 8, par);
          wgmma_wait<0>();
          ACC_FENCE(S1, 96);
          PROF(13);
          STAGE_V(S1 + 64);
          STG_ARRIVE();
          REL(bar_done + 31 * 8);
          scale32(st, S1, c0, c1);
          PIN(st, 32);
          PROF(16);
          ACC_DEF(kv, 20);
          float e_[16], m_[4];
          KV_MMA(3, 1);
          SCHED_FENCE();
          PROF(14);
          PHI_FIN();
          SCHED_FENCE();
          PROF(15);
          wgmma_wait<0>();
          ACC_FENCE(kv, 20);
          PROF(12);
          { float kp[9]; KV_SEND(kp); _Pragma("unroll") for (int i = 0; i < 3; i++) v[i] = make_uint4(__float_as_uint(kp[3 * i]), __float_as_uint(kp[3 * i + 1]), __float_as_uint(kp[3 * i + 2]), 0u); }
#define VDEF(i0) _Pragma("unroll") for (int i = (i0); i < 6; i++) asm volatile("" : "=r"(v[i].x), "=r"(v[i].y), "=r"(v[i].z), "=r"(v[i].w))
          VDEF(3);
          PROF(17);
        }
#pragma unroll 1
        for (int h = 0; h < 2; h++) {
          const uint32_t pO = sbase + (h ? 3 : 8) * SLOT;
          LANE_CONSTS();
          uint32_t fq[32];
          if (h) { KV_LOAD(1); phiq_a(st, big); PIN(st, 16); PROF(31); }
          PROFH(18, 32);
          SCHED_FENCE();
          phiq_b<1>(fq, st, big); PINU(fq, 16); PIN(st + 16, 16);
          SCHED_FENCE();
          PROFH(8, 9);
          if (h) {
            asm volatile("cp.async.bulk.wait_group.read 0;" ::: "memory");
            mbar_wait(bar_lx, par);
            PROF(30);
            KV_TILE(1);
            STG_ARRIVE();
          }
          SCHED_FENCE();
          if (h == 0) {
            float kp[9];
#pragma unroll
            for (int i = 0; i < 9; i++) kp[i] = KVV(i);
            KV_RECV(kp, 1);
            SCHED_FENCE();
          }
          phiq_b<0>(fq + 16, st + 16, big); PINU(fq + 16, 16);
          PROFH(10, 21);
          if (h) { STG_WAIT(); fence_proxy_async_smem(); }
          wgmma_wait<0>();
          ACC_FENCE(S1, 64);
          PROFH(19, 33);
          float o[4][20];
#define O_MMA(hh) { \
            const uint64_t db = make_desc(pV + (hh) * 8192, 16, 1024); \
            ACC_DEF(o[(hh) * 2], 20); ACC_DEF(o[(hh) * 2 + 1], 20); \
            wgmma_fence(); \
            wgmma_n40_rs<0>(o[(hh) * 2], fq + (hh) * 16, db + 256); wgmma_n40_rs<0>(o[(hh) * 2 + 1], fq + (hh) * 16 + 8, db); \
            wgmma_n40_rs<1>(o[(hh) * 2], fq + (hh) * 16 + 4, db + 384); wgmma_n40_rs<1>(o[(hh) * 2 + 1], fq + (hh) * 16 + 12, db + 128); \
            wgmma_commit(); }
          O_MMA(0);
          SCHED_FENCE();
          PMASKS(true, O_BIT(l));
#pragma unroll
          for (int hh = 0; hh < 2; hh++) {
            wgmma_wait<0>();
            ACC_FENCE(o[hh * 2], 20); ACC_FENCE(o[hh * 2 + 1], 20);
            if (!hh) { O_MMA(1); SCHED_FENCE(); }
            if (hh) PROFH(22, 24);
            const float* x = o[hh * 2];
            const float* y = o[hh * 2 + 1];
            const float sx0 = x[17] * 0x1p-40f, sy0 = y[17] * 0x1p-40f, sx1 = x[19] * 0x1p-40f, sy1 = y[19] * 0x1p-40f;
            const float i0 = rcp_fast(fmaf(fmaf(x[17], 1e-6f, x[16]), sy0, y[16] * sx0)), i1 = rcp_fast(fmaf(fmaf(x[19], 1e-6f, x[18]), sy1, y[18] * sx1));
            const float ax0 = sy0 * i0, ay0 = sx0 * i0, ax1 = sy1 * i1, ay1 = sx1 * i1;
#pragma unroll
            for (int dp = 0; dp < 2; dp++)
              stsm_x4(pO + srowoff + ((hh * 64 + dp * 32 + lhi) ^ lsw),
                      PBIT(pack_bf16(fmaf(x[dp * 8], ax0, y[dp * 8] * ay0), fmaf(x[dp * 8 + 1], ax0, y[dp * 8 + 1] * ay0))),
                      PBIT(pack_bf16(fmaf(x[dp * 8 + 2], ax1, y[dp * 8 + 2] * ay1), fmaf(x[dp * 8 + 3], ax1, y[dp * 8 + 3] * ay1))),
                      (pack_bf16(fmaf(x[dp * 8 + 4], ax0, y[dp * 8 + 4] * ay0), fmaf(x[dp * 8 + 5], ax0, y[dp * 8 + 5] * ay0))),
                      (pack_bf16(fmaf(x[dp * 8 + 6], ax1, y[dp * 8 + 6] * ay1), fmaf(x[dp * 8 + 7], ax1, y[dp * 8 + 7] * ay1))));
          }
          WARP_STORE(&tm_os, pO, jj * 128 + h * 64, mm * 128);
          PROFH(20, 34);
          if (h) break;
          float T_[64];
          scale32(st, S1 + 32, c0, c1);
          PIN(st, 32);
          ACC_DEF(T_, 64);
          XM_ISSUE(); wgmma_commit();
          SCHED_FENCE();
          big = any_big(st);
          SCHED_FENCE();
          PROF(27);
          wgmma_wait<0>(); XM_DONE();
          PROF(28);
          bar_wg(wg);
          WSTEP();
          SCHED_FENCE();
          VDEF(0);
          PROF(29);
        }
      }
      __syncwarp();
      if (elect_one()) mbar_arrive_local(bar_epi);
      bar_wg(wg);
#pragma unroll 1
      while (ub < bar_full + 384) {
        WSTEP();
        if (ub == bar_full + 8 * 41) { asm volatile("cp.async.bulk.wait_group.read 0;" ::: "memory"); PROF(35); }
        if (ub == bar_full + 8 * 42) PROF(36);
      }
      {
        float Wb[32];
        LANE_CONSTS();
        TILE_CONSTS(pK, l < NLAYERS - 1, X_BIT(l));
        if (l < NLAYERS - 1) mbar_wait(bar_full, par ^ 1);
        wgmma_wait<0>();
        ACC_FENCE(S1, 64);
        COPYN(Wb, S1 + 32, 32);
        PROF(37);
        X_OUT(0, S1);
        if (l == NLAYERS - 1) {
          int w; asm volatile("mov.u32 %0, %1;" : "=r"(w) : "r"(warp));
          const int oc = jj * 128 + (w & 1) * 1024, orow = mm * 64 + (w >> 1) * 16 - r0;
          WARP_STORE(&tm_xo, pK, oc, orow);
          { PMASKS(false, 0); X_OUT(1, Wb); }
          WARP_STORE(&tm_xo, pV, oc + 64, orow);
          break;
        }
        PROF(38);
        bar_wg(wg);
        fence_proxy_async_smem();
        FIRST_STEP(l + 1);
        WARP_STORE0(&tm_os, pK, jj * 128, mm * 128 + S_LEN);
        REL(bar_done + 47 * 8);
        PROF(39);
        { PMASKS(false, 0); X_OUT(1, Wb); }
        fence_proxy_async_smem();
      }
    }
    asm volatile("cp.async.bulk.wait_group.read 0;" ::: "memory");
    cluster_sync();
  }
}

typedef CUresult (*PFN_encode)(CUtensorMap*, CUtensorMapDataType, cuuint32_t, void*, const cuuint64_t*, const cuuint64_t*,
                               const cuuint32_t*, const cuuint32_t*, CUtensorMapInterleave, CUtensorMapSwizzle,
                               CUtensorMapL2promotion, CUtensorMapFloatOOBfill);

CUtensorMap make_map(PFN_encode enc, const void* ptr, uint64_t inner, uint64_t outer, uint32_t box_inner, uint32_t box_outer,
                     CUtensorMapSwizzle swz = CU_TENSOR_MAP_SWIZZLE_128B, int promo = CU_TENSOR_MAP_L2_PROMOTION_L2_256B) {
  CUtensorMap m;
  cuuint64_t dims[2] = {inner, outer};
  cuuint64_t strides[1] = {inner * 2};
  cuuint32_t box[2] = {box_inner, box_outer};
  cuuint32_t es[2] = {1, 1};
  enc(&m, CU_TENSOR_MAP_DATA_TYPE_BFLOAT16, 2, const_cast<void*>(ptr), dims, strides, box, es, CU_TENSOR_MAP_INTERLEAVE_NONE,
      swz, (CUtensorMapL2promotion)promo, CU_TENSOR_MAP_FLOAT_OOB_FILL_NONE);
  return m;
}

CUtensorMap make_tile_map(PFN_encode enc, const void* ptr, uint64_t rows, bool by_parity, int promo) {
  CUtensorMap m;
  cuuint64_t dims[4] = {D_MODEL, 16, 2, rows / 32};
  cuuint64_t strides[3] = {by_parity ? 4096u : 2048u, by_parity ? 2048u : 32768u, 65536};
  cuuint32_t box[4] = {64, 16, 2, 4};
  cuuint32_t es[4] = {1, 1, 1, 1};
  enc(&m, CU_TENSOR_MAP_DATA_TYPE_BFLOAT16, 4, const_cast<void*>(ptr), dims, strides, box, es, CU_TENSOR_MAP_INTERLEAVE_NONE,
      CU_TENSOR_MAP_SWIZZLE_128B, (CUtensorMapL2promotion)promo, CU_TENSOR_MAP_FLOAT_OOB_FILL_NONE);
  return m;
}

}

extern "C" void kernel_launch(void* const* d_in, const int* in_sizes, int n_in, void* d_out, int out_size) {
  (void)in_sizes; (void)n_in; (void)out_size;
  static PFN_encode enc = nullptr;
  if (!enc) {
    void* fn = nullptr;
    cudaDriverEntryPointQueryResult qr;
    cudaGetDriverEntryPoint("cuTensorMapEncodeTiled", &fn, cudaEnableDefault, &qr);
    enc = (PFN_encode)fn;
    cudaFuncSetAttribute(mega_kernel, cudaFuncAttributeMaxDynamicSharedMemorySize, SMEM_BYTES);
  }
  Params prm;
  prm.x0 = (const __nv_bfloat16*)d_in[0];
  prm.wA_qkv = (const __nv_bfloat16*)d_in[1];
  prm.wA_o = (const __nv_bfloat16*)d_in[2];
  prm.wB_qkv = (const __nv_bfloat16*)d_in[4];
  prm.wB_phi = (const __nv_bfloat16*)d_in[5];
  prm.wB_o = (const __nv_bfloat16*)d_in[6];
  prm.out = (__nv_bfloat16*)d_out;
  void *obuf = nullptr, *wf = nullptr;
  cudaGetSymbolAddress(&obuf, g_obuf);
  cudaGetSymbolAddress(&wf, g_wfold);
  CUtensorMap tm_x0 = make_tile_map(enc, d_in[0], S_LEN, true, XPROMO);
  CUtensorMap tm_xo = make_map(enc, d_out, 2 * D_MODEL, S_LEN / 2, 64, 16);
  CUtensorMap tm_os = make_map(enc, obuf, D_MODEL, 2 * S_LEN, 64, 16);
  CUtensorMap tm_o = make_tile_map(enc, obuf, 2 * S_LEN, false, OPROMO);
  CUtensorMap tm_wf = make_map(enc, wf, 2048, D_MODEL, 64, 32);
  CUtensorMap tm_wqA = make_map(enc, d_in[1], 3 * D_MODEL, D_MODEL, 64, 32, CU_TENSOR_MAP_SWIZZLE_128B, WPROMO);
  CUtensorMap tm_wqB = make_map(enc, prm.wB_qkv, 3 * D_MODEL, D_MODEL, 64, 32);
  CUtensorMap tm_woA = make_map(enc, prm.wA_o, D_MODEL, D_MODEL, 64, 64);
  CUtensorMap tm_woB = make_map(enc, prm.wB_o, D_MODEL, D_MODEL, 64, 64);
  CUtensorMap tm_phi = make_map(enc, prm.wB_phi, 32, 1024, 32, 128, CU_TENSOR_MAP_SWIZZLE_64B);
  mega_kernel<<<NMAIN + NAUX, 384, SMEM_BYTES>>>(tm_x0, tm_xo, tm_os, tm_o, tm_wf, tm_wqA, tm_wqB, tm_woA, tm_woB, tm_phi, prm);
}
```

```cpp
#include <cuda_runtime.h>
#include <cuda.h>
#include <cuda_bf16.h>
#include <stdint.h>

#define NLAYERS 4

#define HPUMP2 1
#define ASKEW 2
#define FPUMP 3
#define PFGAP 100
#define POLLGAP 120
#define HW1 30
#define XPACE 0x06050401000000ull
#define HW0 18
#define XD 4
#define WFGAP 50
#define EARLY 2
#define BIGLIM 3600.f
#define SUMLO 0x1p-100f
#define SUMHI 0x1p100f
#define XPROMO 2
#define OPROMO 3
#define STAG2 300
#define WPROMO 3
#define SB0 2
#define SB1 4
#define SB2 6
#define PROWS 7
#define SPD0 0
#define SPD1 0
#define SPD2 300
#define FRB 0x3535353535ull
#define NOB 0xFFFFFF00u
#define NO1 ~0u
#define NOX ~0u
#define FD0 0
#define FD1 3
#define RPACE 0x221100
#define RSK 2
namespace {

constexpr int S_LEN = 2048, D_MODEL = 1024;
constexpr int NAUX = 4, NMAIN = 128;
constexpr int SLOT = 16384;
constexpr int QST = 24576;
constexpr int OFF_RA = 6 * SLOT, OFF_S = 10 * SLOT;
constexpr int OFF_HALO = 13 * SLOT, OFF_LNB = OFF_HALO  , OFF_ONES = OFF_HALO + 3072;
constexpr int OFF_ST = OFF_HALO + 7168  , OFF_ID = OFF_HALO + 7680, OFF_PHI = OFF_HALO + 8192;
constexpr int OFF_BAR = 14 * SLOT;
constexpr int OFF_LNA = OFF_BAR + 1024;
constexpr int SMEM_BYTES = OFF_LNA + 2048;
#define WO_ASLOT(par) ((par) ? 0x9876CAB39876CA98ull : 0xBC7698A3BC7698BCull)
constexpr unsigned long long WO_BSLOT = 0x5432105421054210ull;
__device__ __forceinline__ int srcb(int j, int i) { return (i + (i >= j)) & 7; }
__device__ __forceinline__ int kslice(int j, int i) { return i < 2 ? 2 * j + i : (i < 9 ? 2 * srcb(j, i - 2) : 2 * srcb(j, i - 9) + 1); }
__device__ __forceinline__ int wslice(int j, int s) { return 2 * ((s & 7) ? srcb(j, (s & 7) - 1) : j) + (s >> 3); }
constexpr int KVH = 6 * 128 * 4;

struct __align__(128) Flag { unsigned v; unsigned pad[31]; };
struct Flags {
  Flag xready[4][16];
  Flag wfready[8];
  Flag done;
  Flag epoch;
};

__device__ Flags g_flags;
__device__ __nv_bfloat16 g_obuf[2 * S_LEN * D_MODEL];
#define O_BIT(l) ((epoch * NLAYERS + (l) + 1) & 1u)
#define X_BIT(l) ((epoch * (NLAYERS - 1) + (l) + 1) & 1u)
__device__ __nv_bfloat16 g_wfold[D_MODEL * 2048];
__device__ uint4 g_halo[16 * 8 * 512];
__device__ __align__(128) float g_kv[2][32 * KVH];
__device__ __align__(128) uint2 g_colsum[2][1536][2];
__device__ __align__(128) uint2 g_stats[S_LEN * 8];
#define H_BIT(l) (NLAYERS > 2 ? (uint32_t)((l) == 0) : (ep1 & 1))
#define STAT_TAG(l) ((ep1 * NLAYERS + (l) + 1) & 3u)

#define RETRY_COUNT()
#define PRL 3
#define PROFL 1
#define PROFW 0
#define PROFT(i) do {} while (0)
#define PROF(i) do {} while (0)
#define PROFH(i, j) do {} while (0)
#define PROFL3(i) do {} while (0)

__device__ __forceinline__ uint32_t smem_u32(const void* p) { return (uint32_t)__cvta_generic_to_shared(p); }
__device__ __forceinline__ bool elect_one() {
  uint32_t p;
  asm volatile("{\n.reg .pred p;\nelect.sync _|p, 0xffffffff;\nselp.u32 %0, 1, 0, p;\n}\n" : "=r"(p));
  return p != 0;
}
__device__ __forceinline__ void mbar_init(uint32_t bar, uint32_t cnt) {
  asm volatile("mbarrier.init.shared::cta.b64 [%0], %1;" :: "r"(bar), "r"(cnt));
}
__device__ __forceinline__ void mbar_expect_tx(uint32_t bar, uint32_t bytes) {
  asm volatile("mbarrier.arrive.expect_tx.shared::cta.b64 _, [%0], %1;" :: "r"(bar), "r"(bytes) : "memory");
}
#define mbar_wait(bar, parity) \
  asm volatile("{\n.reg .pred p, q;\nW_%=:\nmbarrier.try_wait.parity.shared::cta.b64 p, [%1], %2;\nadd.s32 %0, %0, -1;\n" \
               "setp.gt.and.s32 q, %0, 0, !p;\n@q bra.uni W_%=;\n}\n" : "+r"(budget) : "r"((uint32_t)(bar)), "r"((uint32_t)(parity)) : "memory")
#define mbar_wait_sl(bar, parity) \
  asm volatile("{\n.reg .pred p, q;\nW_%=:\nmbarrier.try_wait.parity.shared::cta.b64 p, [%1], %2, 20000;\nadd.s32 %0, %0, -64;\n" \
               "setp.gt.and.s32 q, %0, 0, !p;\n@q bra.uni W_%=;\n}\n" : "+r"(budget) : "r"((uint32_t)(bar)), "r"((uint32_t)(parity)) : "memory")
__device__ __forceinline__ void mbar_arrive_local(uint32_t bar) {
  asm volatile("mbarrier.arrive.shared::cta.b64 _, [%0];" :: "r"(bar) : "memory");
}
__device__ __forceinline__ void tma_load_2d(uint32_t dst, const CUtensorMap* tm, uint32_t bar, int c0, int c1) {
  asm volatile("cp.async.bulk.tensor.2d.shared::cluster.global.mbarrier::complete_tx::bytes [%0], [%1, {%3, %4}], [%2];"
               :: "r"(dst), "l"(tm), "r"(bar), "r"(c0), "r"(c1) : "memory");
}
__device__ __forceinline__ void tma_load_2d_mc(uint32_t dst, const CUtensorMap* tm, uint32_t bar, int c0, int c1) {
  asm volatile("cp.async.bulk.tensor.2d.shared::cluster.global.mbarrier::complete_tx::bytes.multicast::cluster [%0], [%1, {%3, %4}], [%2], %5;"
               :: "r"(dst), "l"(tm), "r"(bar), "r"(c0), "r"(c1), "h"((uint16_t)3) : "memory");
}
__device__ __forceinline__ void tma_store_2d(const CUtensorMap* tm, uint32_t src, int c0, int c1) {
  asm volatile("cp.async.bulk.tensor.2d.global.shared::cta.bulk_group [%0, {%2, %3}], [%1];"
               :: "l"(tm), "r"(src), "r"(c0), "r"(c1) : "memory");
}
__device__ __forceinline__ void tma_load_t(uint32_t dst, const CUtensorMap* tm, uint32_t bar, int c0, int row) {
  asm volatile("cp.async.bulk.tensor.4d.shared::cluster.global.mbarrier::complete_tx::bytes [%0], [%1, {%3, %5, %5, %4}], [%2];"
               :: "r"(dst), "l"(tm), "r"(bar), "r"(c0), "r"(row >> 5), "r"(0) : "memory");
}
__device__ __forceinline__ void tma_store_t(const CUtensorMap* tm, uint32_t src, int c0, int row) {
  asm volatile("cp.async.bulk.tensor.4d.global.shared::cta.bulk_group [%0, {%2, %4, %4, %3}], [%1];"
               :: "l"(tm), "r"(src), "r"(c0), "r"(row >> 5), "r"(0) : "memory");
}
__device__ __forceinline__ void bulk_commit_wait() {
  asm volatile("cp.async.bulk.commit_group;\ncp.async.bulk.wait_group 0;" ::: "memory");
}
__device__ __forceinline__ void prefetch_tmap(const CUtensorMap* tm) {
  asm volatile("prefetch.tensormap [%0];" :: "l"(tm) : "memory");
}
__device__ __forceinline__ void fence_proxy_async_global() { asm volatile("fence.proxy.async.global;" ::: "memory"); }
__device__ __forceinline__ void fence_proxy_async_smem() { asm volatile("fence.proxy.async.shared::cta;" ::: "memory"); }
__device__ __forceinline__ unsigned ld_relaxed(const unsigned* p) {
  unsigned v;
  asm volatile("ld.relaxed.gpu.global.u32 %0, [%1];" : "=r"(v) : "l"(p) : "memory");
  return v;
}
__device__ __forceinline__ void fence_acquire() { asm volatile("fence.acquire.gpu;" ::: "memory"); }
__device__ __forceinline__ void wait_flag(const unsigned* p, unsigned target) {
  int it = 0;
  while ((int)(ld_relaxed(p) - target) < 0 && ++it < (1 << 20)) {}
  fence_acquire();
}
__device__ __forceinline__ void signal_release(unsigned* p) {
  asm volatile("red.release.gpu.global.add.u32 [%0], 1;" :: "l"(p) : "memory");
}
template <int ID, int N> __device__ __forceinline__ void bar_arrive() { asm volatile("bar.arrive %0, %1;" :: "n"(ID), "n"(N) : "memory"); }
template <int ID, int N> __device__ __forceinline__ void bar_sync() { asm volatile("bar.sync %0, %1;" :: "n"(ID), "n"(N) : "memory"); }
__device__ __forceinline__ void bar_wg(int wg) { asm volatile("bar.sync %0, 128;" :: "r"(2 + wg) : "memory"); }
__device__ __forceinline__ void cluster_sync() {
  asm volatile("barrier.cluster.arrive.relaxed.aligned;\nbarrier.cluster.wait.aligned;" ::: "memory");
}
__device__ __forceinline__ void cluster_wait() { asm volatile("barrier.cluster.wait.acquire.aligned;" ::: "memory"); }
enum { BAR_X1 = 7, BAR_WF = 8  , BAR_SKEW = 10 };

__device__ __forceinline__ void wgmma_fence() { asm volatile("wgmma.fence.sync.aligned;" ::: "memory"); }
__device__ __forceinline__ void wgmma_commit() { asm volatile("wgmma.commit_group.sync.aligned;" ::: "memory"); }
template <int N> __device__ __forceinline__ void wgmma_wait() { asm volatile("wgmma.wait_group.sync.aligned %0;" :: "n"(N) : "memory"); }

template <int scale_d, int tnsp_b = 1> __device__ __forceinline__ void wgmma_n192(float* d, uint64_t descA, uint64_t descB) {
  asm volatile("{\n.reg .pred p;\nsetp.ne.b32 p, %98, 0;\n"
               "wgmma.mma_async.sync.aligned.m64n192k16.f32.bf16.bf16 {%0,%1,%2,%3,%4,%5,%6,%7,%8,%9,%10,%11,%12,%13,%14,%15,%16,%17,%18,%19,%20,%21,%22,%23,%24,%25,%26,%27,%28,%29,%30,%31,%32,%33,%34,%35,%36,%37,%38,%39,%40,%41,%42,%43,%44,%45,%46,%47,%48,%49,%50,%51,%52,%53,%54,%55,%56,%57,%58,%59,%60,%61,%62,%63,%64,%65,%66,%67,%68,%69,%70,%71,%72,%73,%74,%75,%76,%77,%78,%79,%80,%81,%82,%83,%84,%85,%86,%87,%88,%89,%90,%91,%92,%93,%94,%95}, %96, %97, p, 1, 1, 0, %99;\n}\n"
               : "+f"(d[0]), "+f"(d[1]), "+f"(d[2]), "+f"(d[3]), "+f"(d[4]), "+f"(d[5]), "+f"(d[6]), "+f"(d[7]), "+f"(d[8]), "+f"(d[9]), "+f"(d[10]), "+f"(d[11]), "+f"(d[12]), "+f"(d[13]), "+f"(d[14]), "+f"(d[15]), "+f"(d[16]), "+f"(d[17]), "+f"(d[18]), "+f"(d[19]), "+f"(d[20]), "+f"(d[21]), "+f"(d[22]), "+f"(d[23]), "+f"(d[24]), "+f"(d[25]), "+f"(d[26]), "+f"(d[27]), "+f"(d[28]), "+f"(d[29]), "+f"(d[30]), "+f"(d[31]), "+f"(d[32]), "+f"(d[33]), "+f"(d[34]), "+f"(d[35]), "+f"(d[36]), "+f"(d[37]), "+f"(d[38]), "+f"(d[39]), "+f"(d[40]), "+f"(d[41]), "+f"(d[42]), "+f"(d[43]), "+f"(d[44]), "+f"(d[45]), "+f"(d[46]), "+f"(d[47]), "+f"(d[48]), "+f"(d[49]), "+f"(d[50]), "+f"(d[51]), "+f"(d[52]), "+f"(d[53]), "+f"(d[54]), "+f"(d[55]), "+f"(d[56]), "+f"(d[57]), "+f"(d[58]), "+f"(d[59]), "+f"(d[60]), "+f"(d[61]), "+f"(d[62]), "+f"(d[63]), "+f"(d[64]), "+f"(d[65]), "+f"(d[66]), "+f"(d[67]), "+f"(d[68]), "+f"(d[69]), "+f"(d[70]), "+f"(d[71]), "+f"(d[72]), "+f"(d[73]), "+f"(d[74]), "+f"(d[75]), "+f"(d[76]), "+f"(d[77]), "+f"(d[78]), "+f"(d[79]), "+f"(d[80]), "+f"(d[81]), "+f"(d[82]), "+f"(d[83]), "+f"(d[84]), "+f"(d[85]), "+f"(d[86]), "+f"(d[87]), "+f"(d[88]), "+f"(d[89]), "+f"(d[90]), "+f"(d[91]), "+f"(d[92]), "+f"(d[93]), "+f"(d[94]), "+f"(d[95])
               : "l"(descA), "l"(descB), "n"(scale_d), "n"(tnsp_b));
}
template <int scale_d> __device__ __forceinline__ void wgmma4_n192(float* d, uint32_t da, uint32_t db) {
#define R_ "{%0,%1,%2,%3,%4,%5,%6,%7,%8,%9,%10,%11,%12,%13,%14,%15,%16,%17,%18,%19,%20,%21,%22,%23,%24,%25,%26,%27,%28,%29,%30,%31,%32,%33,%34,%35,%36,%37,%38,%39,%40,%41,%42,%43,%44,%45,%46,%47,%48,%49,%50,%51,%52,%53,%54,%55,%56,%57,%58,%59,%60,%61,%62,%63,%64,%65,%66,%67,%68,%69,%70,%71,%72,%73,%74,%75,%76,%77,%78,%79,%80,%81,%82,%83,%84,%85,%86,%87,%88,%89,%90,%91,%92,%93,%94,%95}"
  asm volatile("{\n.reg .pred p, q;\n.reg .b64 a, b;\nsetp.ne.b32 p, %98, 0;\nsetp.eq.b32 q, 0, 0;\nmov.b64 a, {%96, 0x40000040};\nmov.b64 b, {%97, 0x40000040};\n"
               "wgmma.mma_async.sync.aligned.m64n192k16.f32.bf16.bf16 " R_ ", a, b, p, 1, 1, 0, 1;\nadd.s64 a, a, 2;\nadd.s64 b, b, 128;\n"
               "wgmma.mma_async.sync.aligned.m64n192k16.f32.bf16.bf16 " R_ ", a, b, q, 1, 1, 0, 1;\nadd.s64 a, a, 2;\nadd.s64 b, b, 128;\n"
               "wgmma.mma_async.sync.aligned.m64n192k16.f32.bf16.bf16 " R_ ", a, b, q, 1, 1, 0, 1;\nadd.s64 a, a, 2;\nadd.s64 b, b, 128;\n"
               "wgmma.mma_async.sync.aligned.m64n192k16.f32.bf16.bf16 " R_ ", a, b, q, 1, 1, 0, 1;\n}\n"
               : "+f"(d[0]), "+f"(d[1]), "+f"(d[2]), "+f"(d[3]), "+f"(d[4]), "+f"(d[5]), "+f"(d[6]), "+f"(d[7]), "+f"(d[8]), "+f"(d[9]), "+f"(d[10]), "+f"(d[11]), "+f"(d[12]), "+f"(d[13]), "+f"(d[14]), "+f"(d[15]), "+f"(d[16]), "+f"(d[17]), "+f"(d[18]), "+f"(d[19]), "+f"(d[20]), "+f"(d[21]), "+f"(d[22]), "+f"(d[23]), "+f"(d[24]), "+f"(d[25]), "+f"(d[26]), "+f"(d[27]), "+f"(d[28]), "+f"(d[29]), "+f"(d[30]), "+f"(d[31]), "+f"(d[32]), "+f"(d[33]), "+f"(d[34]), "+f"(d[35]), "+f"(d[36]), "+f"(d[37]), "+f"(d[38]), "+f"(d[39]), "+f"(d[40]), "+f"(d[41]), "+f"(d[42]), "+f"(d[43]), "+f"(d[44]), "+f"(d[45]), "+f"(d[46]), "+f"(d[47]), "+f"(d[48]), "+f"(d[49]), "+f"(d[50]), "+f"(d[51]), "+f"(d[52]), "+f"(d[53]), "+f"(d[54]), "+f"(d[55]), "+f"(d[56]), "+f"(d[57]), "+f"(d[58]), "+f"(d[59]), "+f"(d[60]), "+f"(d[61]), "+f"(d[62]), "+f"(d[63]), "+f"(d[64]), "+f"(d[65]), "+f"(d[66]), "+f"(d[67]), "+f"(d[68]), "+f"(d[69]), "+f"(d[70]), "+f"(d[71]), "+f"(d[72]), "+f"(d[73]), "+f"(d[74]), "+f"(d[75]), "+f"(d[76]), "+f"(d[77]), "+f"(d[78]), "+f"(d[79]), "+f"(d[80]), "+f"(d[81]), "+f"(d[82]), "+f"(d[83]), "+f"(d[84]), "+f"(d[85]), "+f"(d[86]), "+f"(d[87]), "+f"(d[88]), "+f"(d[89]), "+f"(d[90]), "+f"(d[91]), "+f"(d[92]), "+f"(d[93]), "+f"(d[94]), "+f"(d[95])
               : "r"(da), "r"(db), "n"(scale_d));
#undef R_
}
template <int scale_d> __device__ __forceinline__ void wgmma4_n128(float* d, uint32_t da, uint32_t db) {
#define R_ "{%0,%1,%2,%3,%4,%5,%6,%7,%8,%9,%10,%11,%12,%13,%14,%15,%16,%17,%18,%19,%20,%21,%22,%23,%24,%25,%26,%27,%28,%29,%30,%31,%32,%33,%34,%35,%36,%37,%38,%39,%40,%41,%42,%43,%44,%45,%46,%47,%48,%49,%50,%51,%52,%53,%54,%55,%56,%57,%58,%59,%60,%61,%62,%63}"
  asm volatile("{\n.reg .pred p, q;\n.reg .b64 a, b;\nsetp.ne.b32 p, %66, 0;\nsetp.eq.b32 q, 0, 0;\nmov.b64 a, {%64, 0x40000040};\nmov.b64 b, {%65, 0x40000040};\n"
               "wgmma.mma_async.sync.aligned.m64n128k16.f32.bf16.bf16 " R_ ", a, b, p, 1, 1, 0, 1;\nadd.s64 a, a, 2;\nadd.s64 b, b, 128;\n"
               "wgmma.mma_async.sync.aligned.m64n128k16.f32.bf16.bf16 " R_ ", a, b, q, 1, 1, 0, 1;\nadd.s64 a, a, 2;\nadd.s64 b, b, 128;\n"
               "wgmma.mma_async.sync.aligned.m64n128k16.f32.bf16.bf16 " R_ ", a, b, q, 1, 1, 0, 1;\nadd.s64 a, a, 2;\nadd.s64 b, b, 128;\n"
               "wgmma.mma_async.sync.aligned.m64n128k16.f32.bf16.bf16 " R_ ", a, b, q, 1, 1, 0, 1;\n}\n"
               : "+f"(d[0]), "+f"(d[1]), "+f"(d[2]), "+f"(d[3]), "+f"(d[4]), "+f"(d[5]), "+f"(d[6]), "+f"(d[7]), "+f"(d[8]), "+f"(d[9]), "+f"(d[10]), "+f"(d[11]), "+f"(d[12]), "+f"(d[13]), "+f"(d[14]), "+f"(d[15]), "+f"(d[16]), "+f"(d[17]), "+f"(d[18]), "+f"(d[19]), "+f"(d[20]), "+f"(d[21]), "+f"(d[22]), "+f"(d[23]), "+f"(d[24]), "+f"(d[25]), "+f"(d[26]), "+f"(d[27]), "+f"(d[28]), "+f"(d[29]), "+f"(d[30]), "+f"(d[31]), "+f"(d[32]), "+f"(d[33]), "+f"(d[34]), "+f"(d[35]), "+f"(d[36]), "+f"(d[37]), "+f"(d[38]), "+f"(d[39]), "+f"(d[40]), "+f"(d[41]), "+f"(d[42]), "+f"(d[43]), "+f"(d[44]), "+f"(d[45]), "+f"(d[46]), "+f"(d[47]), "+f"(d[48]), "+f"(d[49]), "+f"(d[50]), "+f"(d[51]), "+f"(d[52]), "+f"(d[53]), "+f"(d[54]), "+f"(d[55]), "+f"(d[56]), "+f"(d[57]), "+f"(d[58]), "+f"(d[59]), "+f"(d[60]), "+f"(d[61]), "+f"(d[62]), "+f"(d[63])
               : "r"(da), "r"(db), "n"(scale_d));
#undef R_
}
template <int scale_d> __device__ __forceinline__ void wgmma_n32(float* d, uint64_t descA, uint64_t descB) {
  asm volatile("{\n.reg .pred p;\nsetp.ne.b32 p, %18, 0;\n"
               "wgmma.mma_async.sync.aligned.m64n32k16.f32.bf16.bf16 {%0,%1,%2,%3,%4,%5,%6,%7,%8,%9,%10,%11,%12,%13,%14,%15}, %16, %17, p, 1, 1, 0, 1;\n}\n"
               : "+f"(d[0]), "+f"(d[1]), "+f"(d[2]), "+f"(d[3]), "+f"(d[4]), "+f"(d[5]), "+f"(d[6]), "+f"(d[7]), "+f"(d[8]), "+f"(d[9]), "+f"(d[10]), "+f"(d[11]), "+f"(d[12]), "+f"(d[13]), "+f"(d[14]), "+f"(d[15])
               : "l"(descA), "l"(descB), "n"(scale_d));
}
template <int scale_d, int tnsp_a> __device__ __forceinline__ void wgmma_n40(float* d, uint64_t descA, uint64_t descB) {
  asm volatile("{\n.reg .pred p;\nsetp.ne.b32 p, %22, 0;\n"
               "wgmma.mma_async.sync.aligned.m64n40k16.f32.bf16.bf16 {%0,%1,%2,%3,%4,%5,%6,%7,%8,%9,%10,%11,%12,%13,%14,%15,%16,%17,%18,%19}, %20, %21, p, 1, 1, %23, 1;\n}\n"
               : "+f"(d[0]), "+f"(d[1]), "+f"(d[2]), "+f"(d[3]), "+f"(d[4]), "+f"(d[5]), "+f"(d[6]), "+f"(d[7]), "+f"(d[8]), "+f"(d[9]), "+f"(d[10]), "+f"(d[11]), "+f"(d[12]), "+f"(d[13]), "+f"(d[14]), "+f"(d[15]), "+f"(d[16]), "+f"(d[17]), "+f"(d[18]), "+f"(d[19])
               : "l"(descA), "l"(descB), "n"(scale_d), "n"(tnsp_a));
}
template <int scale_d> __device__ __forceinline__ void wgmma_n40_rs(float* d, const uint32_t* a, uint64_t descB) {
  asm volatile("{\n.reg .pred p;\nsetp.ne.b32 p, %25, 0;\n"
               "wgmma.mma_async.sync.aligned.m64n40k16.f32.bf16.bf16 {%0,%1,%2,%3,%4,%5,%6,%7,%8,%9,%10,%11,%12,%13,%14,%15,%16,%17,%18,%19}, {%20,%21,%22,%23}, %24, p, 1, 1, 1;\n}\n"
               : "+f"(d[0]), "+f"(d[1]), "+f"(d[2]), "+f"(d[3]), "+f"(d[4]), "+f"(d[5]), "+f"(d[6]), "+f"(d[7]), "+f"(d[8]), "+f"(d[9]), "+f"(d[10]), "+f"(d[11]), "+f"(d[12]), "+f"(d[13]), "+f"(d[14]), "+f"(d[15]), "+f"(d[16]), "+f"(d[17]), "+f"(d[18]), "+f"(d[19])
               : "r"(a[0]), "r"(a[1]), "r"(a[2]), "r"(a[3]), "l"(descB), "n"(scale_d));
}
__device__ __forceinline__ void wgmma_copy(float* d, uint32_t da, uint64_t descB) {
  asm volatile("{\n.reg .pred p;\n.reg .b64 a;\nsetp.ne.b32 p, 0, 0;\nmov.b64 a, {%64, 0x40000040};\n"
               "wgmma.mma_async.sync.aligned.m64n16k16.f32.bf16.bf16 {%0,%1,%2,%3,%4,%5,%6,%7}, a, %65, p, 1, 1, 0, 0;\nadd.s64 a, a, 2;\n"
               "wgmma.mma_async.sync.aligned.m64n16k16.f32.bf16.bf16 {%8,%9,%10,%11,%12,%13,%14,%15}, a, %65, p, 1, 1, 0, 0;\nadd.s64 a, a, 2;\n"
               "wgmma.mma_async.sync.aligned.m64n16k16.f32.bf16.bf16 {%16,%17,%18,%19,%20,%21,%22,%23}, a, %65, p, 1, 1, 0, 0;\nadd.s64 a, a, 2;\n"
               "wgmma.mma_async.sync.aligned.m64n16k16.f32.bf16.bf16 {%24,%25,%26,%27,%28,%29,%30,%31}, a, %65, p, 1, 1, 0, 0;\nadd.s64 a, a, 1018;\n"
               "wgmma.mma_async.sync.aligned.m64n16k16.f32.bf16.bf16 {%32,%33,%34,%35,%36,%37,%38,%39}, a, %65, p, 1, 1, 0, 0;\nadd.s64 a, a, 2;\n"
               "wgmma.mma_async.sync.aligned.m64n16k16.f32.bf16.bf16 {%40,%41,%42,%43,%44,%45,%46,%47}, a, %65, p, 1, 1, 0, 0;\nadd.s64 a, a, 2;\n"
               "wgmma.mma_async.sync.aligned.m64n16k16.f32.bf16.bf16 {%48,%49,%50,%51,%52,%53,%54,%55}, a, %65, p, 1, 1, 0, 0;\nadd.s64 a, a, 2;\n"
               "wgmma.mma_async.sync.aligned.m64n16k16.f32.bf16.bf16 {%56,%57,%58,%59,%60,%61,%62,%63}, a, %65, p, 1, 1, 0, 0;\n"
               "}\n"
               : "+f"(d[0]), "+f"(d[1]), "+f"(d[2]), "+f"(d[3]), "+f"(d[4]), "+f"(d[5]), "+f"(d[6]), "+f"(d[7]), "+f"(d[8]), "+f"(d[9]), "+f"(d[10]), "+f"(d[11]), "+f"(d[12]), "+f"(d[13]), "+f"(d[14]), "+f"(d[15]), "+f"(d[16]), "+f"(d[17]), "+f"(d[18]), "+f"(d[19]), "+f"(d[20]), "+f"(d[21]), "+f"(d[22]), "+f"(d[23]), "+f"(d[24]), "+f"(d[25]), "+f"(d[26]), "+f"(d[27]), "+f"(d[28]), "+f"(d[29]), "+f"(d[30]), "+f"(d[31]), "+f"(d[32]), "+f"(d[33]), "+f"(d[34]), "+f"(d[35]), "+f"(d[36]), "+f"(d[37]), "+f"(d[38]), "+f"(d[39]), "+f"(d[40]), "+f"(d[41]), "+f"(d[42]), "+f"(d[43]), "+f"(d[44]), "+f"(d[45]), "+f"(d[46]), "+f"(d[47]), "+f"(d[48]), "+f"(d[49]), "+f"(d[50]), "+f"(d[51]), "+f"(d[52]), "+f"(d[53]), "+f"(d[54]), "+f"(d[55]), "+f"(d[56]), "+f"(d[57]), "+f"(d[58]), "+f"(d[59]), "+f"(d[60]), "+f"(d[61]), "+f"(d[62]), "+f"(d[63])
               : "r"(da), "l"(descB));
}
template <int scale_d> __device__ __forceinline__ void wgmma_n192_rs(float* d, const uint32_t* a, uint32_t db) {
  asm volatile("{\n.reg .pred p;\n.reg .b64 b;\nsetp.ne.b32 p, %101, 0;\nmov.b64 b, {%100, 0x40000040};\n"
               "wgmma.mma_async.sync.aligned.m64n192k16.f32.bf16.bf16 {%0,%1,%2,%3,%4,%5,%6,%7,%8,%9,%10,%11,%12,%13,%14,%15,%16,%17,%18,%19,%20,%21,%22,%23,%24,%25,%26,%27,%28,%29,%30,%31,%32,%33,%34,%35,%36,%37,%38,%39,%40,%41,%42,%43,%44,%45,%46,%47,%48,%49,%50,%51,%52,%53,%54,%55,%56,%57,%58,%59,%60,%61,%62,%63,%64,%65,%66,%67,%68,%69,%70,%71,%72,%73,%74,%75,%76,%77,%78,%79,%80,%81,%82,%83,%84,%85,%86,%87,%88,%89,%90,%91,%92,%93,%94,%95}, {%96,%97,%98,%99}, b, p, 1, 1, 1;\n}\n"
               : "+f"(d[0]), "+f"(d[1]), "+f"(d[2]), "+f"(d[3]), "+f"(d[4]), "+f"(d[5]), "+f"(d[6]), "+f"(d[7]), "+f"(d[8]), "+f"(d[9]), "+f"(d[10]), "+f"(d[11]), "+f"(d[12]), "+f"(d[13]), "+f"(d[14]), "+f"(d[15]), "+f"(d[16]), "+f"(d[17]), "+f"(d[18]), "+f"(d[19]), "+f"(d[20]), "+f"(d[21]), "+f"(d[22]), "+f"(d[23]), "+f"(d[24]), "+f"(d[25]), "+f"(d[26]), "+f"(d[27]), "+f"(d[28]), "+f"(d[29]), "+f"(d[30]), "+f"(d[31]), "+f"(d[32]), "+f"(d[33]), "+f"(d[34]), "+f"(d[35]), "+f"(d[36]), "+f"(d[37]), "+f"(d[38]), "+f"(d[39]), "+f"(d[40]), "+f"(d[41]), "+f"(d[42]), "+f"(d[43]), "+f"(d[44]), "+f"(d[45]), "+f"(d[46]), "+f"(d[47]), "+f"(d[48]), "+f"(d[49]), "+f"(d[50]), "+f"(d[51]), "+f"(d[52]), "+f"(d[53]), "+f"(d[54]), "+f"(d[55]), "+f"(d[56]), "+f"(d[57]), "+f"(d[58]), "+f"(d[59]), "+f"(d[60]), "+f"(d[61]), "+f"(d[62]), "+f"(d[63]), "+f"(d[64]), "+f"(d[65]), "+f"(d[66]), "+f"(d[67]), "+f"(d[68]), "+f"(d[69]), "+f"(d[70]), "+f"(d[71]), "+f"(d[72]), "+f"(d[73]), "+f"(d[74]), "+f"(d[75]), "+f"(d[76]), "+f"(d[77]), "+f"(d[78]), "+f"(d[79]), "+f"(d[80]), "+f"(d[81]), "+f"(d[82]), "+f"(d[83]), "+f"(d[84]), "+f"(d[85]), "+f"(d[86]), "+f"(d[87]), "+f"(d[88]), "+f"(d[89]), "+f"(d[90]), "+f"(d[91]), "+f"(d[92]), "+f"(d[93]), "+f"(d[94]), "+f"(d[95])
               : "r"(a[0]), "r"(a[1]), "r"(a[2]), "r"(a[3]), "r"(db), "n"(scale_d));
}
__device__ __forceinline__ uint64_t make_desc(uint32_t addr, uint32_t lbo_bytes, uint32_t sbo_bytes) {
  return (uint64_t)((addr & 0x3FFFF) >> 4) | ((uint64_t)(lbo_bytes >> 4) << 16) | ((uint64_t)(sbo_bytes >> 4) << 32) | (1ull << 62);
}

__device__ __forceinline__ void ldsm_x4(uint32_t addr, uint32_t& r0, uint32_t& r1, uint32_t& r2, uint32_t& r3) {
  asm volatile("ldmatrix.sync.aligned.m8n8.x4.shared.b16 {%0,%1,%2,%3}, [%4];" : "=r"(r0), "=r"(r1), "=r"(r2), "=r"(r3) : "r"(addr) : "memory");
}
__device__ __forceinline__ void ldsm_x4_t(uint32_t addr, uint32_t& r0, uint32_t& r1, uint32_t& r2, uint32_t& r3) {
  asm volatile("ldmatrix.sync.aligned.m8n8.x4.trans.shared.b16 {%0,%1,%2,%3}, [%4];" : "=r"(r0), "=r"(r1), "=r"(r2), "=r"(r3) : "r"(addr) : "memory");
}
__device__ __forceinline__ void stsm_x4(uint32_t addr, uint32_t r0, uint32_t r1, uint32_t r2, uint32_t r3) {
  asm volatile("stmatrix.sync.aligned.m8n8.x4.shared.b16 [%0], {%1,%2,%3,%4};" :: "r"(addr), "r"(r0), "r"(r1), "r"(r2), "r"(r3) : "memory");
}
__device__ __forceinline__ void stsm_x4_t(uint32_t addr, uint32_t r0, uint32_t r1, uint32_t r2, uint32_t r3) {
  asm volatile("stmatrix.sync.aligned.m8n8.x4.trans.shared.b16 [%0], {%1,%2,%3,%4};" :: "r"(addr), "r"(r0), "r"(r1), "r"(r2), "r"(r3) : "memory");
}
__device__ __forceinline__ void sts128(uint32_t addr, uint32_t a, uint32_t b, uint32_t c, uint32_t d) {
  asm volatile("st.shared.v4.u32 [%0], {%1,%2,%3,%4};" :: "r"(addr), "r"(a), "r"(b), "r"(c), "r"(d) : "memory");
}
__device__ __forceinline__ float lds32f(uint32_t addr) {
  float v;
  asm volatile("ld.shared.f32 %0, [%1];" : "=f"(v) : "r"(addr) : "memory");
  return v;
}
__device__ __forceinline__ void sts32f(uint32_t addr, float a) {
  asm volatile("st.shared.f32 [%0], %1;" :: "r"(addr), "f"(a) : "memory");
}
__device__ __forceinline__ void mma_bf16(float (&c)[4], uint32_t a0, uint32_t a1, uint32_t a2, uint32_t a3, uint32_t b0, uint32_t b1) {
  asm volatile("mma.sync.aligned.m16n8k16.row.col.f32.bf16.bf16.f32 {%0,%1,%2,%3}, {%4,%5,%6,%7}, {%8,%9}, {%0,%1,%2,%3};"
               : "+f"(c[0]), "+f"(c[1]), "+f"(c[2]), "+f"(c[3]) : "r"(a0), "r"(a1), "r"(a2), "r"(a3), "r"(b0), "r"(b1));
}
__device__ __forceinline__ void mma_bf16_z(float (&c)[4], uint32_t a0, uint32_t a1, uint32_t a2, uint32_t a3, uint32_t b0, uint32_t b1) {
  asm volatile("mma.sync.aligned.m16n8k16.row.col.f32.bf16.bf16.f32 {%0,%1,%2,%3}, {%4,%5,%6,%7}, {%8,%9}, {%10,%10,%10,%10};"
               : "=f"(c[0]), "=f"(c[1]), "=f"(c[2]), "=f"(c[3]) : "r"(a0), "r"(a1), "r"(a2), "r"(a3), "r"(b0), "r"(b1), "f"(0.f));
}
__device__ __forceinline__ uint32_t movm_t(uint32_t v) {
  uint32_t r;
  asm volatile("movmatrix.sync.aligned.m8n8.trans.b16 %0, %1;" : "=r"(r) : "r"(v));
  return r;
}
__device__ __forceinline__ uint32_t pack_bf16(float lo, float hi) {
  uint32_t r;
  asm("cvt.rn.bf16x2.f32 %0, %1, %2;" : "=r"(r) : "f"(hi), "f"(lo));
  return r;
}
__device__ __forceinline__ float bf_lo(uint32_t v) { return __uint_as_float(v << 16); }
__device__ __forceinline__ float bf_hi(uint32_t v) { return __uint_as_float(v & 0xFFFF0000u); }
__device__ __forceinline__ void split3(float x, uint32_t& h, uint32_t& m, uint32_t& l) {
  h = pack_bf16(x, 0.f); x -= bf_lo(h);
  m = pack_bf16(x, 0.f); x -= bf_lo(m);
  l = pack_bf16(x, 0.f);
}
__device__ __forceinline__ float ex2(float x) { float r; asm("ex2.approx.ftz.f32 %0, %1;" : "=f"(r) : "f"(x)); return r; }
__device__ __forceinline__ float rcp_fast(float x) { float r; asm("rcp.approx.ftz.f32 %0, %1;" : "=f"(r) : "f"(x)); return r; }
__device__ __forceinline__ void red_v4(float* p, float a, float b, float c, float d) {
  asm volatile("red.global.add.v4.f32 [%0], {%1, %2, %3, %4};" :: "l"(p), "f"(a), "f"(b), "f"(c), "f"(d) : "memory");
}
__device__ __forceinline__ uint4 ld_ll(const uint4* p) {
  uint4 v;
  asm volatile("{\n.reg .b64 a, b;\nld.relaxed.gpu.global.v2.b64 {a, b}, [%4];\nmov.b64 {%0, %1}, a;\nmov.b64 {%2, %3}, b;\n}\n"
               : "=r"(v.x), "=r"(v.y), "=r"(v.z), "=r"(v.w) : "l"(p) : "memory");
  return v;
}
__device__ __forceinline__ void st_b64(uint2* p, uint32_t a, uint32_t b) {
  asm volatile("{\n.reg .b64 v;\nmov.b64 v, {%1, %2};\nst.relaxed.gpu.global.b64 [%0], v;\n}\n" :: "l"(p), "r"(a), "r"(b) : "memory");
}
__device__ __forceinline__ void st_b128(uint4* p, uint32_t a, uint32_t b, uint32_t c, uint32_t d) {
  asm volatile("{\n.reg .b128 v;\nmov.b128 v, {%1, %2, %3, %4};\nst.relaxed.gpu.global.b128 [%0], v;\n}\n" :: "l"(p), "r"(a), "r"(b), "r"(c), "r"(d) : "memory");
}
__device__ __forceinline__ uint4 ld_b128(const uint4* p) {
  uint4 v;
  asm volatile("{\n.reg .b128 v;\nld.relaxed.gpu.global.b128 v, [%4];\nmov.b128 {%0, %1, %2, %3}, v;\n}\n" : "=r"(v.x), "=r"(v.y), "=r"(v.z), "=r"(v.w) : "l"(p) : "memory");
  return v;
}

constexpr float LOG2E = 1.4426950408889634f;

struct Params {
  const __nv_bfloat16* x0;
  const __nv_bfloat16* wA_qkv;
  const __nv_bfloat16* wA_o;
  const __nv_bfloat16* wB_qkv;
  const __nv_bfloat16* wB_phi;
  const __nv_bfloat16* wB_o;
  __nv_bfloat16* out;
};

#define ACC_DEF(d, n) _Pragma("unroll") for (int i_ = 0; i_ < (n); i_++) asm volatile("" : "=f"(d[i_]))
#define ACC_FENCE(d, n) _Pragma("unroll") for (int i_ = 0; i_ < (n); i_++) asm volatile("" : "+f"(d[i_]) :: "memory")
#define PIN(a, n) _Pragma("unroll") for (int i_ = 0; i_ < (n); i_++) asm volatile("" : "+f"((a)[i_]))
#define PINU(a, n) _Pragma("unroll") for (int i_ = 0; i_ < (n); i_++) asm volatile("" : "+r"((a)[i_]))

#define V_ADDR(p0, sw) uint32_t va_[2] = {(p0) + (srowoff >> 1) + (lhi ^ lsw2 ^ (sw)), (p0) + (srowoff >> 1) + ((32 + lhi) ^ lsw2 ^ (sw))}
#define STAGE_V(acc) { \
    _Pragma("unroll") for (int j_ = 0; j_ < 4; j_++) { \
      const float* a_ = (acc) + j_ * 8; \
      stsm_x4(va_[j_ & 1] + (j_ >> 1) * 8192, \
              pack_bf16(rs0 * a_[0], rs0 * a_[1]), pack_bf16(rs1 * a_[2], rs1 * a_[3]), pack_bf16(rs0 * a_[4], rs0 * a_[5]), pack_bf16(rs1 * a_[6], rs1 * a_[7])); } }
#define FRAG(dst, acc, TR, grp) { \
    _Pragma("unroll") for (int i_ = 15; i_ >= 0; i_--) { \
      const float r_ = (i_ & 8) ? rs1 : rs0; \
      const uint32_t w_ = pack_bf16(r_ * (acc)[4 * (i_ & 7) + (i_ >> 3) * 2], r_ * (acc)[4 * (i_ & 7) + (i_ >> 3) * 2 + 1]); \
      (dst)[8 + i_] = (TR) ? movm_t(w_) : w_; \
      if (i_ == 8 && warp >= 6 && mm < 15) { \
        _Pragma("unroll") for (int j_ = 0; j_ < 2; j_++) \
          st_b128(g_halo + (size_t)(mm * 8 + jj) * 512 + ((grp) * 4 + warp * 2 - 12 + j_) * 32 + lane, ((dst)[16 + j_ * 4] & ~1u) | H_BIT(l), (dst)[17 + j_ * 4], (dst)[18 + j_ * 4], (dst)[19 + j_ * 4]); } } \
    PINU((dst) + 8, 16); }
#define FRAG_PUT(src, slot) if (warp < 6) { _Pragma("unroll") for (int j_ = 0; j_ < 2; j_++) \
      sts128(sbase + OFF_S + (slot) * 8192 + 2048 + warp * 1024 + j_ * 512 + lane * 16, (src)[j_ * 4], (src)[j_ * 4 + 1], (src)[j_ * 4 + 2], (src)[j_ * 4 + 3]); }
#define FRAG_GET(dst, slot) { _Pragma("unroll") for (int j_ = 0; j_ < 2; j_++) \
      asm volatile("ld.shared.v4.u32 {%0, %1, %2, %3}, [%4];" : "=r"((dst)[j_ * 4]), "=r"((dst)[j_ * 4 + 1]), "=r"((dst)[j_ * 4 + 2]), "=r"((dst)[j_ * 4 + 3]) \
                   : "r"(sbase + OFF_S + (slot) * 8192 + warp * 1024 + j_ * 512 + lane * 16) : "memory"); }
#define RW(j) (((j) >> 1) * 4 + ((j) & 1))
template <int POS> __device__ __forceinline__ float exps16_(float* o, const float* p) {
  float s[4];
#pragma unroll
  for (int j = 0; j < 16; j++) { o[j] = ex2(POS ? p[RW(j)] : -p[RW(j)]); if (j < 4) s[j] = o[j]; else s[j & 3] += o[j]; }
  const float r = (s[0] + s[1]) + (s[2] + s[3]);
  return r + __shfl_xor_sync(0xffffffffu, r, 1);
}
template <int POS> __device__ __forceinline__ void exps16_fix(float* o, const float* p, float& sum) {
  if (__builtin_expect(__any_sync(0xffffffffu, !(sum > SUMLO && sum < SUMHI)), 0)) {
    float m = p[0], q[32];
#pragma unroll
    for (int j = 1; j < 16; j++) m = POS ? fmaxf(m, p[RW(j)]) : fminf(m, p[RW(j)]);
    const float x = __shfl_xor_sync(0xffffffffu, m, 1);
    m = POS ? fmaxf(m, x) : fminf(m, x);
#pragma unroll
    for (int j = 0; j < 16; j++) q[RW(j)] = p[RW(j)] - m;
    sum = exps16_<POS>(o, q);
  }
}
__device__ __forceinline__ void store16(const float* e, float sum, uint32_t dst, uint32_t dsw, int c0) {
  const float inv = rcp_fast(sum);
#pragma unroll
  for (int j = 0; j < 2; j++)
    sts128(dst + (((c0 + j) << 4) ^ dsw), pack_bf16(e[j * 8] * inv, e[j * 8 + 1] * inv), pack_bf16(e[j * 8 + 2] * inv, e[j * 8 + 3] * inv),
           pack_bf16(e[j * 8 + 4] * inv, e[j * 8 + 5] * inv), pack_bf16(e[j * 8 + 6] * inv, e[j * 8 + 7] * inv));
}
template <int POS> __device__ __forceinline__ void expp16(uint32_t* o, float* p) {
  {
#pragma unroll
    for (int r = 0; r < 4; r += 2) {
      float m = p[r];
#pragma unroll
      for (int j = 1; j < 8; j++) m = POS ? fmaxf(m, p[r + RW(j)]) : fminf(m, p[r + RW(j)]);
#pragma unroll
      for (int s = 1; s <= 2; s <<= 1) { const float x = __shfl_xor_sync(0xffffffffu, m, s); m = POS ? fmaxf(m, x) : fminf(m, x); }
#pragma unroll
      for (int j = 0; j < 8; j++) p[r + RW(j)] -= m;
    }
  }
#pragma unroll
  for (int j = 0; j < 8; j++) o[j] = pack_bf16(ex2(POS ? p[2 * j] : -p[2 * j]), ex2(POS ? p[2 * j + 1] : -p[2 * j + 1]));
}
__device__ __forceinline__ void scale32(float* o, const float* p, float c0, float c1) {
#pragma unroll
  for (int i = 0; i < 32; i++) asm volatile("mul.f32 %0, %1, %2;" : "=f"(o[i]) : "f"(p[i]), "f"((i & 2) ? c1 : c0));
}
__device__ __forceinline__ bool any_big(const float* p) {
  float m[4];
#pragma unroll
  for (int i = 0; i < 32; i++) m[i >> 3] = (i & 7) ? fmaf(p[i], p[i], m[i >> 3]) : p[i] * p[i];
  return __any_sync(0xffffffffu, !(fmaxf(fmaxf(m[0], m[1]), fmaxf(m[2], m[3])) < BIGLIM));
}
__device__ __forceinline__ void phiq_a(float* p, bool big) {
  if (__builtin_expect(!big, 1)) {
#pragma unroll
    for (int j = 0; j < 16; j++) p[j] = ex2(p[j]);
  }
}
template <int NEXT> __device__ __forceinline__ void phiq_b(uint32_t* o, float* p, bool big) {
  if (__builtin_expect(big, 0)) {
    expp16<0>(o, p); expp16<1>(o + 8, p);
  } else {
    if (NEXT) phiq_a(p + 16, false);
#pragma unroll
    for (int j = 0; j < 4; j++) {
      const float a = p[4 * j], b = p[4 * j + 1], c = p[4 * j + 2], d = p[4 * j + 3];
      const float ab = a * b, cd = c * d, r = rcp_fast(ab * cd), x = r * cd, y = r * ab;
      o[2 * j] = pack_bf16(x * b, x * a); o[2 * j + 1] = pack_bf16(y * d, y * c);
      o[8 + 2 * j] = pack_bf16(a, b); o[9 + 2 * j] = pack_bf16(c, d);
    }
  }
}
#define SCHED_FENCE() asm volatile("pmevent 0;" ::: "memory")

__global__ void __cluster_dims__(2, 1, 1) __launch_bounds__(384, 1)
mega_kernel(const __grid_constant__ CUtensorMap tm_x0, const __grid_constant__ CUtensorMap tm_xo, const __grid_constant__ CUtensorMap tm_os,
            const __grid_constant__ CUtensorMap tm_o, const __grid_constant__ CUtensorMap tm_wf,
            const __grid_constant__ CUtensorMap tm_wqA, const __grid_constant__ CUtensorMap tm_wqB,
            const __grid_constant__ CUtensorMap tm_woA, const __grid_constant__ CUtensorMap tm_woB,
            const __grid_constant__ CUtensorMap tm_phi, const Params prm) {
  extern __shared__ __align__(1024) uint8_t smem_raw[];
  const uint32_t sbase = smem_u32(smem_raw);
  const uint32_t bar_full = sbase + OFF_BAR;
  const uint32_t bar_done = bar_full + 384;
  const uint32_t bar_stat = bar_full + 768, bar_stat2 = bar_full + 776, bar_epi = bar_full + 784, bar_phi = bar_full + 936  , bar_halo = bar_full + 904  ;
  const uint32_t bar_xr = bar_full + 800, bar_lx = bar_full + 808, bar_stg = bar_full + 832;
  const uint32_t bar_chk = bar_full + 848;

  const int warp = __shfl_sync(0xffffffffu, threadIdx.x >> 5, 0), lane = threadIdx.x & 31;
  const uint32_t bar_kx = sbase + OFF_ID + 384 + warp * 8;
  uint32_t rank;
  asm volatile("mov.u32 %0, %%cluster_ctarank;" : "=r"(rank));
  const int aux = (int)blockIdx.x - NMAIN, tp = (int)(blockIdx.x >> 1) - 4;
  const int gp = tp < 0 ? 0 : (tp < 32 ? tp & 7 : 1 + (tp - 32) % 7), me = tp < 0 ? tp + 8 : (tp < 32 ? tp >> 3 : 4 + (tp - 32) / 7);
  const int jj = me, cc = gp;
  const int cta = aux >= 0 ? -1 : (cc * 8 + jj) * 2 + (int)rank;
  const int mm = cc * 2 + (int)rank;

#define LOAD_EPOCH() const unsigned epoch = ld_relaxed(&g_flags.epoch.v), ep1 = epoch + 1; (void)epoch
  int budget = 1 << 22;
  unsigned epoch0 = 0;

  if (cta >= 0) {
    if (warp >= 8 && warp < 8 + EARLY && elect_one()) {
      const int u = warp - 8;
      const uint32_t fb = bar_full + u * 8;
      mbar_init(fb, 1);
      asm volatile("fence.mbarrier_init.release.cluster;" ::: "memory");
      fence_proxy_async_smem();
      mbar_expect_tx(fb, QST + SLOT);
      if (u) __nanosleep(STAG2);
      tma_load_t(sbase + OFF_S + u * SLOT, &tm_x0, fb, jj * 128 + u * 64, mm * 128);
#pragma unroll
      for (int i = 0; i < 6; i++) tma_load_2d(sbase + u * QST + i * 4096, &tm_wqA, fb, jj * 128 + (i >> 1) * 1024, jj * 128 + u * 64 + (i & 1) * 32);
      if (u == 0) PROFT(472);
    }
    __syncwarp();
    {
      const int tx = threadIdx.x;
      const __nv_bfloat16* pf = (tx < 128) ? prm.x0 + (size_t)(mm * 128 + tx) * D_MODEL + jj * 128
                                           : prm.wA_qkv + (size_t)(jj * 128 + (tx & 63)) * 3072 + ((tx - 128) >> 6) * 1024 + jj * 128 + rank * 64;
      if (tx < 320) asm volatile("prefetch.global.L2 [%0];" :: "l"(pf));
      else if (tx == 320) prefetch_tmap(&tm_x0);
      else if (tx == 352) prefetch_tmap(&tm_wqA);
      else if (tx == 383) epoch0 = ld_relaxed(&g_flags.epoch.v);
    }
    if (elect_one()) {
#pragma unroll
      for (int i = 0; i < 4; i++) {
        const int u = warp * 4 + i;
        if (u >= EARLY) mbar_init(bar_full + u * 8, ((u >= 4 && u < 11) || (u > 32 && u != 40)) ? 2 : 1); mbar_init(bar_done + u * 8, 16);
      }
      mbar_init(bar_stat + warp * 16, 0x111111181182ull >> (4 * warp) & 15);
      mbar_init(bar_stat + warp * 16 + 8, 0x111111121811ull >> (4 * warp) & 15);
      mbar_init(bar_chk + 112 + (warp & 7) * 8, 1);
      mbar_init(bar_kx, 1);
      asm volatile("fence.mbarrier_init.release.cluster;" ::: "memory");
    }
    __syncwarp();
    __syncthreads();
    asm volatile("barrier.cluster.arrive.relaxed.aligned;" ::: "memory");
  }

  if (cta < 0) {
    LOAD_EPOCH();
    const uint32_t buf = sbase + warp * SLOT, bar = sbase + OFF_BAR + warp * 16;
    const uint32_t lsw = (lane & 7) << 4, lhi = (lane >> 4) << 4, lrow = (lane & 15) * 128;
    const bool el = elect_one();
    if (el) {
      mbar_init(bar, 1); mbar_init(bar + 8, 1);
      asm volatile("fence.mbarrier_init.release.cluster;" ::: "memory");
    }
#pragma unroll 1
    for (int rd = 0; rd < (NLAYERS > 1 ? 5 : 2); rd++) {
      if (rd >= 2 && warp >= 8) break;
      const int tk = rd < 2 ? aux * 12 + warp : aux * 8 + warp;
      const int half = tk & 1;
      const int blk = rd < 2 ? (tk >> 1) * 2 + rd : (4 - rd) * 16 + (tk >> 1);
      const CUtensorMap* tm = rd < 2 ? &tm_wqA : (rd == 2 ? &tm_wqB : &tm_wf);
      const int j0 = (blk & 15) >> 1;
#define AUX_LOAD(n) { const uint32_t d_ = buf + ((n) & 1) * 8192, b_ = bar + ((n) & 1) * 8; const int r_ = kslice(j0, 2 * (n) + half) * 64; \
        mbar_expect_tx(b_, 8192); tma_load_2d(d_, tm, b_, blk * 64, r_); tma_load_2d(d_ + 4096, tm, b_, blk * 64, r_ + 32); }
      if (el) {
        if (rd == 3) { wait_flag(&g_flags.wfready[j0].v, ep1 * 16); fence_proxy_async_global(); }
        AUX_LOAD(0); AUX_LOAD(1);
      }
      __syncwarp();
      float cs[8][4];
#pragma unroll
      for (int i = 0; i < 8; i++) cs[i][0] = cs[i][1] = cs[i][2] = cs[i][3] = 0.f;
#pragma unroll 1
      for (int n = 0; n < 8; n++) {
        const uint32_t tb = buf + (n & 1) * 8192 + lrow;
        mbar_wait(bar + (n & 1) * 8, (n >> 1) & 1);
#pragma unroll
        for (int i = 0; i < 16; i++) {
          uint32_t b0, b1, b2, b3;
          ldsm_x4_t(tb + (i >> 2) * 2048 + (((i & 3) * 32 + lhi) ^ lsw), b0, b1, b2, b3);
          mma_bf16(cs[2 * (i & 3)], 0x3F803F80u, 0x3F803F80u, 0x3F803F80u, 0x3F803F80u, b0, b1);
          mma_bf16(cs[2 * (i & 3) + 1], 0x3F803F80u, 0x3F803F80u, 0x3F803F80u, 0x3F803F80u, b2, b3);
        }
        __syncwarp();
        if (el && n < 6) AUX_LOAD(n + 2);
        __syncwarp();
      }
      if (lane < 4) {
#pragma unroll
        for (int i = 0; i < 8; i++) st_b64(&g_colsum[rd >= 2][blk * 32 + i * 4 + lane][half], __float_as_uint(cs[i][0]), (__float_as_uint(cs[i][1]) & ~3u) | (ep1 & 3));
      }
      __syncwarp();
    }
  } else if (warp >= 8) {
    asm volatile("setmaxnreg.dec.sync.aligned.u32 40;");
    if (warp == 8) {
      const bool el = elect_one();
      cluster_wait();
      if (el) {
#pragma unroll 1
        for (int l = 0; l < NLAYERS; l++) {
          const uint32_t par = l & 1;
          const CUtensorMap* tqk = par ? &tm_wf : &tm_wqA;
          const CUtensorMap* tv = par ? &tm_wqB : &tm_wqA;
          const CUtensorMap* two = par ? &tm_woB : &tm_woA;
          if (l == 1) { LOAD_EPOCH(); wait_flag(&g_flags.wfready[jj].v, ep1 * 16); fence_proxy_async_global(); }
#pragma unroll 1
          for (int u = l ? 0 : EARLY; u < 32; u++) {
            if (u >= 4) mbar_wait_sl(bar_done + (u - 4) * 8, par);
            else if (l) mbar_wait_sl(bar_done + (43 + u + (u >> 1)) * 8, par ^ 1);
            else mbar_wait_sl(bar_full, 0);
            const uint32_t fb = bar_full + u * 8;
            const bool res = u < 11 || (u >= 18 && u < 22);
            mbar_expect_tx(fb, res ? QST : QST + SLOT);
            const int row = kslice(jj, u < 4 ? u & 1 : (u < 18 ? u - 2 : (u < 22 ? u - 6 : u - 20))) * 64 + (int)rank * 32;
            const int ps = u < 4 ? u >> 1 : (u >= 18), col = jj * 128 + ps * 64;
            const int c0 = par ? jj * 128 + (ps ? 0 : 1024) : col;
            const uint32_t dst = sbase + (u & 3) * QST + rank * 4096;
            tma_load_2d_mc(dst, tqk, fb, c0, row);
            tma_load_2d_mc(dst + 8192, tqk, fb, c0 + (par ? 64 : 1024), row);
            tma_load_2d_mc(dst + 16384, tv, fb, col + 2048, row);
            if (u < 8) PROFL3(472 + u);
          }
#pragma unroll 1
          for (int s = 0; s < 16; s++) {
            if (s < 5) { if (s != 2 && s != 4) mbar_wait_sl(bar_done + (28 + s) * 8, par); }
            else if (s != 14) mbar_wait_sl(bar_done + (27 + s - (s == 15)) * 8, par);
            const uint32_t fb = bar_full + (32 + s) * 8;
            mbar_expect_tx(fb, SLOT);
            tma_load_2d_mc(sbase + rank * 8192 + (uint32_t)((WO_BSLOT >> (4 * s)) & 15) * SLOT, two, fb, jj * 128 + (int)rank * 64, wslice(jj, s) * 64);
            const int ts = s + 1;
            if (s >= 5 && ts < 8) {
              mbar_expect_tx(bar_chk - 8 + ts * 8, SLOT);
              tma_load_t(sbase + (uint32_t)((WO_ASLOT(par) >> (4 * ts)) & 15) * SLOT, &tm_o, bar_chk - 8 + ts * 8, wslice(jj, ts) * 64, mm * 128);
            }
          }
        }
      }
      __syncwarp();
    } else if (warp == 9) {
      const bool el = elect_one();
      LOAD_EPOCH();
#pragma unroll 1
      for (int lp = 0; lp < 4 * NLAYERS; lp++) {
        const int l = lp >> 2, ph = lp & 3;
        if (ph == 3) continue;
        const uint32_t par = l & 1;
        const unsigned* pp = reinterpret_cast<const unsigned*>(g_obuf + (ph >> 1) * 64 + (size_t)(mm * 128 + (ph ? 0 : S_LEN) + ((lane & 7) | PROWS) * 16 + (jj & 1) * 8) * D_MODEL +
                                                               (jj >> 1) * 16 + srcb(jj, lane >> 3) * 128);
        const CUtensorMap* tm = lp ? &tm_o : &tm_x0;
        const int row = mm * 128 + ((ph || !l) ? 0 : S_LEN);
        const uint32_t bit = ph ? O_BIT(l) : X_BIT(l - 1);
        const uint32_t slots = ph ? (uint32_t)(WO_ASLOT(par) >> (ph * 32 - 28)) : 0x8769876u;
        const unsigned long long fr = ph == 0 ? XPACE : ph == 1 ? (par ? FRB : 0x35351F1E1Dull) : 0x27262524232232ull;
        uint32_t no = (lp == 0 || (lp & 7) == 1) ? 0 : (ph == 1 ? NOB : (ph ? NO1 : NOX)), v0 = 0, v1 = 0;
        mbar_wait_sl(ph ? bar_done + ((uint32_t)fr & 63) * 8 : (l ? bar_done + 47 * 8 : bar_full), ph ? par : (l ? par ^ 1 : 0));
        if (el && ph) PROFT(324 + l * 16 + ph);
        __syncwarp();
        if (no && (ph == 1 ? SPD1 : (ph ? SPD2 : SPD0))) __nanosleep(ph == 1 ? SPD1 : (ph ? SPD2 : SPD0));
        if (no) { v0 = ld_relaxed(pp); if (ph != 1) __nanosleep(POLLGAP); v1 = ld_relaxed(pp); }
#pragma unroll 1
        for (int i = 0; i < (ph == 1 ? 5 : 7); i++, no >>= 8) {
          uint32_t op[4] = {(lp ? bar_chk + (ph >> 1) * 112 : bar_full + 32) + i * 8  , sbase + ((slots >> (4 * i)) & 15) * SLOT,
                            (uint32_t)(srcb(jj, i) * 128 + (ph >> 1) * 64), bar_done + ((uint32_t)(fr >> (8 * i)) & 63) * 8};
          PINU(op, 4);
          if (el) mbar_expect_tx(op[0], SLOT);
#pragma unroll 1
          for (int it = 0; (no & 0xFF) && it < (1 << 18); it++) {
            no &= __ballot_sync(0xffffffffu, (v0 ^ bit) & 1) >> (8 * i);
            if (no) v0 = ld_relaxed(pp);
            if (!(no & 0xFF)) break;
            no &= __ballot_sync(0xffffffffu, (v1 ^ bit) & 1) >> (8 * i);
            if (no) v1 = ld_relaxed(pp);
          }
          if (i >= (ph ? 1 : 4)) mbar_wait_sl(op[3], par);
          if (el) {
            if (i == 0) PROFT(320 + l * 16 + ph);
            PROFL3(448 + ph * 8 + i);
            tma_load_t(op[1], tm, op[0], op[2], row);
          }
          __syncwarp();
        }
        if (ph == 0 && el) {
          if (l) { wait_flag(&g_flags.xready[l][mm].v, ep1 * 8); fence_proxy_async_global(); }
#pragma unroll 1
          for (int u = 11; u < 34; u++) {
            if (u == 18) u = 22;
            mbar_wait_sl(bar_done + (u - 4) * 8, par);
            if (u == 32) mbar_expect_tx(bar_xr, 2 * SLOT);
            tma_load_t(sbase + OFF_RA + (u & 3) * SLOT, tm, u < 32 ? bar_full + u * 8 : bar_xr, kslice(jj, u < 18 ? u - 2 : (u < 32 ? u - 20 : u - 32)) * 64, row);
          }
        }
        __syncwarp();
      }
      if (el && atomicAdd(&g_flags.done.v, 1) == ep1 * NMAIN - 1) asm volatile("st.relaxed.gpu.global.u32 [%0], %1;" :: "l"(&g_flags.epoch.v), "r"(ep1) : "memory");
      __syncwarp();
      cluster_wait();
    } else {
      const int hw = warp - 10;
      const unsigned epoch = hw ? __shfl_sync(0xffffffffu, epoch0, 31) : ld_relaxed(&g_flags.epoch.v), ep1 = epoch + 1;
      const bool el = elect_one();
      cluster_wait();
      if (hw == 0) {
        mbar_wait_sl(bar_full + 8, 0);
        if (lane < 7) prefetch_tmap(lane == 0 ? &tm_os : lane == 1 ? &tm_o : lane == 2 ? &tm_wf : lane == 3 ? &tm_wqB : lane == 4 ? &tm_woA : lane == 5 ? &tm_woB : &tm_phi);
#pragma unroll 1
        for (int i = 0; i < (NLAYERS > 1 ? 9 : 0); i++) {
          if (i == 0 || i == 5) mbar_wait_sl(bar_done + (i ? FD1 : FD0) * 8, 0);
          if (el) {
            if (i == 0) { mbar_expect_tx(bar_phi, 2 * SLOT + 8192); tma_load_2d(sbase + OFF_PHI, &tm_phi, bar_phi, 0, jj * 128); }
            else tma_load_2d(sbase + (i > 4 ? 10 : 12) * SLOT - 4096 + i * 4096, &tm_wqB, bar_phi, (i > 4 ? 896 : 0) + jj * 128 + ((i - 1) >> 1) * 64, mm * 64 + (~i & 1) * 32);
          }
          __syncwarp();
          __nanosleep(PFGAP);
        }
      } else {
        if (lane < 24) {
          const uint32_t one = (lane & 8) ? 0u : 0x3F80u << ((lane & 1) * 16), w = (lane >> 1) & 3;
          sts128(sbase + OFF_ID + lane * 16, w == 0 ? one : 0u, w == 1 ? one : 0u, w == 2 ? one : 0u, w == 3 ? one : 0u);
        }
#pragma unroll 1
        for (int b = 0; b < 2; b++) {
          float4* z = reinterpret_cast<float4*>(g_kv[b] + (jj * 4) * KVH + mm * (4 * KVH / 16)) + lane;
#pragma unroll
          for (int i = 0; i < 6; i++) z[i * 32] = make_float4(0.f, 0.f, 0.f, 0.f);
        }
#pragma unroll 1
        for (int i = 0; i < 16; i++) {
          const int b = i >> 2;
          const uint32_t v = (b == 0 ? O_BIT(0) : b == 1 ? X_BIT(0) : H_BIT(0)) + 1;
          uint4* p = b < 2 ? reinterpret_cast<uint4*>(g_obuf + (size_t)(b * S_LEN + mm * 128 + (i & 3) * 32 + (lane >> 3) * 8) * D_MODEL + jj * 128 + (b ? 0 : 64)) + (lane & 7)
                           : g_halo + (size_t)(mm * 8 + jj) * 512 + i * 32 + lane;
          *p = make_uint4(v, v, v, v);
        }
        fence_proxy_async_global();
      }
      __syncwarp();
      uint32_t chkp = 0;
#pragma unroll 1
      for (int lp = hw; lp < 8 * NLAYERS; lp++) {
        const int l = lp >> 3, tk = lp & 7, ph = tk ? 2 - hw : 0;
        const uint32_t par = l & 1;
        int lane; asm volatile("mov.u32 %0, %%laneid;" : "=r"(lane));
        if (tk == 5 || (hw && tk == 0)) {
          const uint32_t bit = ph ? O_BIT(l) : X_BIT(l - 1);
          uint32_t slots = ph ? (uint32_t)(WO_ASLOT(par) >> (ph * 32 - 28)) : 0x8769876u;
          const uint32_t a0 = sbase + (lane & 7) * 126 + lane * 4 + (lane & 1) * 14;
#pragma unroll 1
          for (int c = 0; c < 7; c++, slots >>= 4) {
            const uint32_t cb = bar_chk + 112 - hw * 112 + c * 8;
#pragma unroll 1
            for (int it = 0; it < (1 << 12); it++) {
              mbar_wait_sl(cb, (chkp >> c) & 1);
              chkp ^= 1u << c;
              if (el) PROFL3(384 + ph * 8 + c);
              uint32_t bad;
              asm volatile("{\n.reg .b32 w<16>;\n"
                           "ld.shared.u32 w0, [%1 + 0];\n"
                           "ld.shared.u32 w1, [%1 + 1024];\n"
                           "ld.shared.u32 w2, [%1 + 2048];\n"
                           "ld.shared.u32 w3, [%1 + 3072];\n"
                           "ld.shared.u32 w4, [%1 + 4096];\n"
                           "ld.shared.u32 w5, [%1 + 5120];\n"
                           "ld.shared.u32 w6, [%1 + 6144];\n"
                           "ld.shared.u32 w7, [%1 + 7168];\n"
                           "ld.shared.u32 w8, [%1 + 8192];\n"
                           "ld.shared.u32 w9, [%1 + 9216];\n"
                           "ld.shared.u32 w10, [%1 + 10240];\n"
                           "ld.shared.u32 w11, [%1 + 11264];\n"
                           "ld.shared.u32 w12, [%1 + 12288];\n"
                           "ld.shared.u32 w13, [%1 + 13312];\n"
                           "ld.shared.u32 w14, [%1 + 14336];\n"
                           "ld.shared.u32 w15, [%1 + 15360];\n"
                           "lop3.b32 w0, w0, w1, %2, 0x7E;\n"
                           "lop3.b32 w2, w2, w3, %2, 0x7E;\n"
                           "lop3.b32 w4, w4, w5, %2, 0x7E;\n"
                           "lop3.b32 w6, w6, w7, %2, 0x7E;\n"
                           "lop3.b32 w8, w8, w9, %2, 0x7E;\n"
                           "lop3.b32 w10, w10, w11, %2, 0x7E;\n"
                           "lop3.b32 w12, w12, w13, %2, 0x7E;\n"
                           "lop3.b32 w14, w14, w15, %2, 0x7E;\n"
                           "lop3.b32 w0, w0, w2, w4, 0xFE;\nlop3.b32 w6, w6, w8, w10, 0xFE;\nlop3.b32 w0, w0, w12, w14, 0xFE;\nlop3.b32 %0, w0, w6, 1, 0xA8;\n}\n"
                           : "=r"(bad) : "r"(a0 + (slots & 15) * SLOT), "r"(bit) : "memory");
              if (__all_sync(0xffffffffu, bad == 0)) break;
              if (el) {
                fence_proxy_async_smem();
                mbar_expect_tx(cb, SLOT);
                tma_load_t(sbase + (slots & 15) * SLOT, &tm_o, cb, srcb(jj, c) * 128 + (ph >> 1) * 64, mm * 128 + (ph ? 0 : S_LEN));
                RETRY_COUNT();
              }
              __syncwarp();
            }
            if (el) { mbar_arrive_local(bar_full + (c + (ph ? 25 + ph * 8 : 4)) * 8); PROFL3(416 + ph * 8 + c); }
            __syncwarp();
          }
        } else if (hw && (tk & 5) == 1) {
          {
            const int hp = tk >> 1;
            const uint4* src = reinterpret_cast<const uint4*>(g_colsum[par][jj * 64 + hp * 32 + lane]);
            uint32_t bad;
            int it = 0;
            float c[6];
            do {
              bad = 0;
#pragma unroll
              for (int p = 0; p < 3; p++) {
                const uint4 v = ld_ll(src + ((par && p < 2) ? (hp ? -32 : 512) + p * 32 : p * 512));
                bad |= (v.y ^ ep1) | (v.w ^ ep1);
                c[2 * p] = __uint_as_float(v.x) + __uint_as_float(v.z); c[2 * p + 1] = __uint_as_float(v.y) + __uint_as_float(v.w);
              }
              bad &= 3;
              if (bad) __nanosleep(300);
            } while (bad && ++it < (1 << 16));
#pragma unroll
            for (int p = 0; p < 6; p++) {
              uint32_t h, m, lo;
              split3(c[p], h, m, lo);
              sts128(sbase + OFF_LNB + hp * 4096 + (p >> 1) * 1024 + lane * 32 + (p & 1) * 16, h | (m << 16), h | (lo << 16), h | (m << 16), lo | (m << 16));
            }
            fence_proxy_async_smem();
            __syncwarp();
            if (el) { mbar_arrive_local(hp ? bar_stat2 : bar_stat); if (hp == 0) PROFT(324 + l * 16); }
            __syncwarp();
          }
        } else if (tk == 0) {
          mbar_wait_sl(bar_done + 24, par);
          const uint4* sp = reinterpret_cast<const uint4*>(g_stats + (size_t)(mm * 128) * 8) + lane;
#pragma unroll 1
          for (int hf = 0; hf < 4; hf++) {
            uint4 v[4];
            uint32_t bad;
            int it = 0;
            do {
              bad = 0;
#pragma unroll
              for (int i = 0; i < 4; i++) { v[i] = ld_ll(sp + (hf * 4 + i) * 32); bad |= (v[i].y ^ STAT_TAG(l)) | (v[i].w ^ STAT_TAG(l)); }
              bad &= 3;
              if (bad) __nanosleep(200);
            } while (bad && ++it < (1 << 16));
            __syncwarp();
            float mean = 0.f, m2 = 0.f;
#pragma unroll
            for (int i = 0; i < 4; i++) {
              float a = __uint_as_float(v[i].x) + __uint_as_float(v[i].z);
              a += __shfl_xor_sync(0xffffffffu, a, 1); a += __shfl_xor_sync(0xffffffffu, a, 2);
              a *= 0.125f;
              const float e0 = __uint_as_float(v[i].x) - a, e1 = __uint_as_float(v[i].z) - a;
              float q = fmaf(fmaf(e0, e0, e1 * e1), 128.f, __uint_as_float(v[i].y) + __uint_as_float(v[i].w));
              q += __shfl_xor_sync(0xffffffffu, q, 1); q += __shfl_xor_sync(0xffffffffu, q, 2);
              if ((lane & 3) == i) { mean = a; m2 = q; }
            }
            const uint32_t row = hf * 32 + (lane & 3) * 8 + (lane >> 2);
            uint32_t h, m, lo;
            split3(-0.5f * mean, h, m, lo);
            sts128(sbase + OFF_LNA + row * 16, h | (h << 16), m | (h << 16), lo | (m << 16), m | (lo << 16));
            sts32f(sbase + OFF_ST + row * 4, rsqrtf(m2 * (1.f / 1024.f) + 1e-5f));
          }
          fence_proxy_async_smem();
          __syncwarp();
          if (el) { mbar_arrive_local(bar_stat); PROFT(323 + l * 16); }
          __syncwarp();
#pragma unroll 1
          for (int i = 0; i < 8 - 4 * l; i++) {
            asm volatile("prefetch.global.L2 [%0];" :: "l"(i < 4 ? (l ? prm.wB_o : prm.wA_o) + (size_t)cta * 8192 + i * 2048 + lane * 64
                                                                 : prm.wB_qkv + (size_t)(cta * 8 + (i - 4) * 2 + (lane >> 4)) * 3072 + 2048 + (lane & 15) * 64));
            __nanosleep(PFGAP);
          }
        } else if (lp == 3) {
#pragma unroll 1
          for (int c = 0; c < (NLAYERS > 1 ? 8 : 0); c++) {
            if (!(c & 3)) { asm volatile("bar.sync %0, 288;" :: "r"(BAR_WF + (c >> 2)) : "memory"); fence_proxy_async_smem(); }
            if (el) {
              tma_store_2d(&tm_wf, sbase + 11 * SLOT + c * 4096, (c < 4 ? 1024 : -128) + jj * 128 + (c >> 1) * 64, mm * 64 + (c & 1) * 32);
              if (c == 7) {
                asm volatile("cp.async.bulk.commit_group;\ncp.async.bulk.wait_group.read 0;" ::: "memory");
                mbar_arrive_local(bar_phi + 8);
              } else __nanosleep(WFGAP);
            }
            __syncwarp();
          }
          if (el) { bulk_commit_wait(); signal_release(&g_flags.wfready[jj].v); PROFT(335); }
          __syncwarp();
        } else if (tk == 2 || tk == 4) {
          if (par) continue;
          const int i = tk >> 2;
          mbar_wait_sl(bar_done + (i ? HW1 : (hw ? 19 : HW0)) * 8, 0);
          const uint4* src = g_halo + (size_t)(mm * 8 + jj - 8) * 512 + i * 256 + hw * 128 + lane;
          uint4 v[4];
          int it = 0;
          bool ok;
          do {
#pragma unroll
            for (int j = 0; j < 4; j++) v[j] = mm ? ld_b128(src + j * 32) : make_uint4(H_BIT(l), 0, 0, 0);
            ok = __all_sync(0xffffffffu, (((v[0].x ^ H_BIT(l)) | (v[1].x ^ H_BIT(l)) | (v[2].x ^ H_BIT(l)) | (v[3].x ^ H_BIT(l))) & 1) == 0);
          } while (!ok && ++it < (1 << 16));
#pragma unroll
          for (int j = 0; j < 4; j++) sts128(sbase + OFF_S + hw * 8192 + j * 512 + lane * 16, v[j].x, v[j].y, v[j].z, v[j].w);
          __syncwarp();
          if (el) { mbar_arrive_local(bar_halo + hw * 8); PROFT(331 + l * 16 + i * 2 + hw); }
          __syncwarp();
        } else if (tk == 6 && hw == 0 && l < NLAYERS - 1) {
          bar_sync<BAR_X1, 288>();
          if (el) {
            PROFT(328 + l * 16);
            mbar_wait_sl(bar_full + XD * 8, par ^ 1);
            tma_store_t(&tm_o, sbase + 11 * SLOT, jj * 128 + 64, mm * 128 + S_LEN);
            bulk_commit_wait();
            signal_release(&g_flags.xready[l + 1][mm].v);
            PROFT(330 + l * 16);
          }
          __syncwarp();
        }
      }
    }
    cluster_sync();
  } else {
    asm volatile("setmaxnreg.inc.sync.aligned.u32 232;");
    const int wg = warp >> 2;
    const int r0 = warp * 16;
    const uint32_t pK = sbase + OFF_S, pV = sbase + OFF_S + SLOT;
#define PMASKS(on, bit) const uint32_t pm0 = ((on) && t == (g >> 1)), pbit = (bit)
#define PBIT(w) (((w) & ~pm0) | (pbit & pm0))
#define LANE_CONSTS() \
    int lane; asm volatile("mov.u32 %0, %%laneid;" : "=r"(lane)); \
    const int g = lane >> 2, t = lane & 3; \
    const uint32_t srowoff = (r0 + (lane & 15)) * 128, lsw = (lane & 7) << 4, lhi = (lane >> 4) << 4, lsw2 = (lane & 6) << 3; \
    (void)g; (void)t; (void)srowoff; (void)lsw; (void)lhi; (void)lsw2;
    uint32_t stgp = 0, peer;
    asm volatile("mapa.shared::cluster.u32 %0, %1, %2;" : "=r"(peer) : "r"(sbase), "r"(rank ^ 1));
    peer -= sbase;
    const uint32_t dA0 = (((sbase & 0x3FFFF) + wg * 8192) >> 4) | 0x10000u, dB0 = ((sbase & 0x3FFFF) >> 4) | 0x2000000u;
    cluster_wait();
#define DESC(lo, hi) ((uint64_t)(uint32_t)(lo) | ((uint64_t)(hi) << 32))
#define STG_ARRIVE() { __syncwarp(); if (elect_one()) mbar_arrive_local(bar_stg); }
#define STG_WAIT() { mbar_wait(bar_stg, stgp); stgp ^= 1; }
#define PROFS() do {} while (0)
#define REL(addr) { if (elect_one()) { mbar_arrive_local(addr); asm volatile("mbarrier.arrive.shared::cluster.b64 _, [%0];" :: "r"((addr) + peer) : "memory"); } }
#define QSTEP(ACC, DA, SC) { \
      const uint32_t da = (DA), db = dB0 + (ub & 0x18) * (QST >> 7); \
      mbar_wait(ub, par); \
      wgmma_fence(); \
      wgmma4_n192<SC>(ACC, da, db); \
      wgmma_commit(); PROFS(); }
#define QREL() { wgmma_wait<1>(); REL(ub + 376); ub += 8; }
#define RA_CUR (dA0 + (OFF_RA >> 4) + (ub & 0x18) * (SLOT >> 7))
#define PUMP1() { QSTEP(S1, RA_CUR, 1); QREL(); }
#define PUMPN() { wgmma_fence(); wgmma4_n192<1>(S1, RA_CUR, dB0 + (ub & 0x18) * (QST >> 7)); wgmma_commit(); PROFS(); QREL(); }
#define PUMP0() { PUMP1(); SCHED_FENCE(); }
#define WSTEP() { \
      const uint32_t s4 = (ub - bar_full - 256) >> 1; \
      const uint32_t da = dA0 + (((uint32_t)(WO_ASLOT(par) >> s4) & 15) << 10), db = dB0 + (((uint32_t)(WO_BSLOT >> s4) & 15) << 10); \
      mbar_wait(ub, par); \
      wgmma_fence(); \
      wgmma4_n128<1>(S1, da, db); \
      wgmma_commit(); PROFS(); \
      wgmma_wait<1>(); \
      if (s4) REL(ub + 376); \
      ub += 8; }
#define PUMPS(n) { _Pragma("unroll 1") for (int i_ = 0; i_ < (n); i_++) PUMP1(); }
#define LNSTEP(ACC, hh) { wgmma_fence(); wgmma_n192<1, 0>(ACC, make_desc(sbase + OFF_LNA + wg * 1024, 0, 128) ^ (1ull << 62), make_desc(sbase + OFF_LNB + (hh) * 4096, 0, 128) ^ (1ull << 62)); }
#define WARP_STORE(tm, tile, col, row) { fence_proxy_async_smem(); __syncwarp(); WARP_STORE0(tm, tile, col, row); }
#define WARP_STORE0(tm, tile, col, row) { \
      if (elect_one()) { tma_store_2d(tm, (tile) + r0 * 128, col, (row) + r0); asm volatile("cp.async.bulk.commit_group;" ::: "memory"); } __syncwarp(); }
#define TILE_CONSTS(base, on, bit) \
      uint32_t ta[5]; \
      { PMASKS(on, bit); (void)pbit; ta[4] = pm0; } \
      _Pragma("unroll") for (int j = 0; j < 4; j++) ta[j] = (base) + srowoff + ((((uint32_t)j << 5) + lhi) ^ lsw); \
      PINU(ta, 5); SCHED_FENCE(); \
      const uint32_t pm0 = ta[4], pbit = (bit)
#define X_OUT(pc, W) { \
      _Pragma("unroll") for (int j = 0; j < 4; j++) \
        stsm_x4(ta[j] + (pc) * SLOT, \
                PBIT(pack_bf16((W)[j * 8 + 0], (W)[j * 8 + 1])), PBIT(pack_bf16((W)[j * 8 + 2], (W)[j * 8 + 3])), \
                (pack_bf16((W)[j * 8 + 4], (W)[j * 8 + 5])), (pack_bf16((W)[j * 8 + 6], (W)[j * 8 + 7]))); }
#define REST_P1(SKEW) { \
      mbar_wait(bar_stat2, par); \
      LNSTEP(S1, 1); \
      wgmma_commit(); \
      _Pragma("unroll 1") while (ub < bar_full + 256) { \
        const bool hold = ub == bar_full + 256 - 8 * (SKEW) && wg == 0; \
        if (hold) { wgmma_wait<0>(); REL(ub + 376); bar_sync<BAR_SKEW, 256>(); } \
        QSTEP(S1, RA_CUR, 1); \
        if (ub == bar_full + 248 && wg == 1) bar_arrive<BAR_SKEW, 256>(); \
        wgmma_wait<1>(); if (!hold) REL(ub + 376); ub += 8; \
      } \
      mbar_wait(bar_done + (31 - (SKEW)) * 8, par);        \
      wgmma_wait<0>(); \
      ACC_FENCE(S1, 96); \
      REL(bar_done + 31 * 8); \
      PROF(13); }
#define FOLD(tile, rd) { \
          LANE_CONSTS(); \
          float d[32]; \
          ACC_DEF(d, 32); \
          mbar_wait(bar_phi, 0); \
          wgmma_fence(); \
          _Pragma("unroll") for (int i = 0; i < 2; i++) { \
            const uint64_t da = make_desc((tile) + wg * 8192 + i * 64, 16, 1024); \
            const uint64_t db = make_desc(sbase + OFF_PHI + wg * 4096 + i * 2048, 16, 512) ^ (3ull << 62); \
            wgmma_n32<0>(d + i * 16, da, db); wgmma_n32<1>(d + i * 16, da + 2, db + 64); \
          } \
          wgmma_commit(); \
          PUMP0(); \
          ACC_FENCE(d, 32); \
          bar_wg(wg); \
          _Pragma("unroll") for (int i = 0; i < 4; i++) { \
            const float* x = d + (i & 1) * 8 + (i >> 1) * 2; \
            if (rd) sts128((tile) + wg * 8192 + ((warp & 3) * 16 + (i >> 1) * 8 + g) * 128 + (((2 * t + (i & 1)) ^ g) << 4), \
                           pack_bf16(x[0], x[1]), pack_bf16(x[4], x[5]), pack_bf16(x[16], x[17]), pack_bf16(x[20], x[21])); \
            else stsm_x4((tile) + srowoff + ((((uint32_t)i << 5) + lhi) ^ lsw), pack_bf16(d[i * 8], d[i * 8 + 1]), pack_bf16(d[i * 8 + 2], d[i * 8 + 3]), \
                         pack_bf16(d[i * 8 + 4], d[i * 8 + 5]), pack_bf16(d[i * 8 + 6], d[i * 8 + 7])); \
          } \
          }
#define XM_ISSUE() { mbar_wait(bar_xr, par); wgmma_fence(); \
      wgmma_copy(T_, dA0 + (OFF_RA >> 4), make_desc(sbase + OFF_ID, 128, 128) ^ (1ull << 62)); }
#define COPYN(d, s, n) _Pragma("unroll") for (int i_ = 0; i_ < (n); i_++) { uint32_t c_; asm volatile("mov.b32 %0, %1;" : "=r"(c_) : "f"((s)[i_])); (d)[i_] = __uint_as_float(c_); }
#define COPY64(d, s) COPYN(d, s, 64)
#define XM_DONE() { ACC_FENCE(T_, 64); COPY64(S1, T_); ACC_FENCE(S1, 64); \
      __syncwarp(); if (elect_one()) mbar_arrive_local(bar_lx); }
#define LOAD_X() { float T_[64]; ACC_DEF(T_, 64); wgmma_wait<0>(); XM_ISSUE(); wgmma_commit(); wgmma_wait<0>(); XM_DONE(); }

    float S0[96], S1[96];
#define FIRST_STEP(l_) { const int ln_ = (l_), l = ln_; const uint32_t ub = bar_full; (void)l; (void)ub; ACC_DEF(S0, 96); wgmma_fence(); wgmma4_n192<0>(S0, dA0 + (OFF_S >> 4), dB0); wgmma_commit(); PROFS(); }
    LOAD_EPOCH();
    mbar_wait(bar_full, 0);
    FIRST_STEP(0);
#pragma unroll 1
    for (int l = 0;; l++) {
      const uint32_t par = l & 1;
      uint32_t ub = bar_full + 8;
      PROF(1);
      {
        LANE_CONSTS();
        uint32_t ta[4];
#pragma unroll
        for (int j = 0; j < 4; j++) ta[j] = pK + srowoff + ((((uint32_t)j << 5) + lhi) ^ lsw);
        float p0, p1, a0 = 0.f, a1 = 0.f, q0 = 0.f, q1 = 0.f;
#define STATS(j0, j1) _Pragma("unroll") for (int j = (j0); j < (j1); j++) { \
          uint32_t x[4]; \
          ldsm_x4(ta[j & 3] + (j >> 2) * SLOT, x[0], x[1], x[2], x[3]); \
          if (j == 0) { p0 = __shfl_sync(0xffffffffu, bf_lo(x[0]), lane & 28); p1 = __shfl_sync(0xffffffffu, bf_lo(x[1]), lane & 28); } \
          _Pragma("unroll") for (int i = 0; i < 4; i += 2) { \
            const float d0 = bf_lo(x[i]) - p0, d1 = bf_hi(x[i]) - p0, d2 = bf_lo(x[i + 1]) - p1, d3 = bf_hi(x[i + 1]) - p1; \
            a0 += d0 + d1; a1 += d2 + d3; \
            q0 = fmaf(d1, d1, fmaf(d0, d0, q0)); q1 = fmaf(d3, d3, fmaf(d2, d2, q1)); } } \
          asm volatile("" : "+f"(a0), "+f"(a1), "+f"(q0), "+f"(q1), "+f"(p0), "+f"(p1)); SCHED_FENCE()
        if (SB0) { STATS(0, SB0); }
        bar_wg(wg);
        QSTEP(S0, dA0 + ((OFF_S + SLOT) >> 4), 1);
        QREL();
        SCHED_FENCE();
        STATS(SB0, SB1);
        ACC_DEF(S1, 96);
        QSTEP(S1, dA0 + (OFF_S >> 4), 0);
        QREL();
        SCHED_FENCE();
        STATS(SB1, SB2);
        QSTEP(S1, dA0 + ((OFF_S + SLOT) >> 4), 1);
        QREL();
        SCHED_FENCE();
        STATS(SB2, 8);
#pragma unroll
        for (int o = 1; o <= 2; o <<= 1) {
          a0 += __shfl_xor_sync(0xffffffffu, a0, o); a1 += __shfl_xor_sync(0xffffffffu, a1, o);
          q0 += __shfl_xor_sync(0xffffffffu, q0, o); q1 += __shfl_xor_sync(0xffffffffu, q1, o);
        }
        if (t == 1) { a0 = a1; q0 = q1; p0 = p1; }
        if (t < 2) st_b64(g_stats + (size_t)(mm * 128 + r0 + g + t * 8) * 8 + jj, __float_as_uint(fmaf(a0, 1.f / 128.f, p0)),
                          (__float_as_uint(fmaxf(fmaf(a0 * (-1.f / 128.f), a0, q0), 0.f)) & ~3u) | STAT_TAG(l));
        if (l) { asm volatile("cp.async.bulk.wait_group 0;" ::: "memory"); bar_arrive<BAR_X1, 288>(); }
#pragma unroll 1
        for (int i = 0; i < 14; i++) {
          QSTEP(S0, RA_CUR, 1);
          if (i == 0) PROF(2);
          QREL();
        }
      }
      LANE_CONSTS();
      mbar_wait(bar_stat, par);
      LNSTEP(S0, 0);
      wgmma_commit();
      const float rs0 = lds32f(sbase + OFF_ST + (r0 + g) * 4), rs1 = lds32f(sbase + OFF_ST + (r0 + g + 8) * 4);
      PUMP0();
      ACC_FENCE(S0, 96);
      PROF(3);
      if (!par) {
        constexpr uint32_t par = 0;
        uint32_t qa[16];
        uint32_t kf[24], vf[24];
#define DRAIN_A(ACC, hp, PMP) { \
          LANE_CONSTS(); \
          FRAG(kf, ACC + 32, 0, (hp) * 2); \
          PMP; \
          FRAG(vf, ACC + 64, 1, (hp) * 2 + 1); \
          _Pragma("unroll") for (int i_ = 0; i_ < 16; i_++) qa[i_] = pack_bf16(ACC[2 * i_], ACC[2 * i_ + 1]); \
          PINU(qa, 16); }
        DRAIN_A(S0, 0, PUMP0());
        if (l == 0 && NLAYERS > 1) {
#pragma unroll 1
          for (int rd = 1; rd >= 0; rd--) {
            FOLD(sbase + (12 - rd) * SLOT, rd);
            asm volatile("bar.arrive %0, 288;" :: "r"(BAR_WF + 1 - rd) : "memory");
          }
        }
        PUMPS(FPUMP);
#pragma unroll 1
        for (int h = 0; h < 2; h++) {
          PROFH(4, 16);
          LANE_CONSTS();
          FRAG_PUT(kf + 16, 0); FRAG_PUT(vf + 16, 1);
          STG_ARRIVE();
          if (h) { PROF(8); LOAD_X(); PROF(9); WSTEP(); PROF(10); } else PUMPS(HPUMP2);
          const bool gt0 = 2 * t > g, gt1 = 2 * t >= g;
          uint32_t msk[2] = {(gt0 ? 0xFFFFu : 0u) | (gt1 ? 0xFFFF0000u : 0u), g == 2 * t ? 0x10001u : 0u};
          PINU(msk, 2);
          TILE_CONSTS(sbase, false, 0);
          (void)pm0; (void)pbit;
          if (h) PROF(12);
          STG_WAIT();
          if (h) PROF(14);
          if (warp < 2) mbar_wait(bar_halo, h);
          if (h) PROF(15);
          if (h == 0) mbar_wait(ub, par);
          FRAG_GET(kf, 0);
          PROFH(5, 17);
          float s[2][3][4];
#pragma unroll
          for (int ks = 0; ks < 2; ks++)
#pragma unroll
            for (int i = 0; i < 6; i++) {
              const int hh = i & 1, jb = 2 - (i >> 1);
              const uint32_t* b = kf + jb * 8 + hh * 4 + ks * 2;
              if (ks) mma_bf16(s[hh][jb], qa[hh * 8 + 4], qa[hh * 8 + 5], qa[hh * 8 + 6], qa[hh * 8 + 7], b[0], b[1]);
              else mma_bf16_z(s[hh][jb], qa[hh * 8], qa[hh * 8 + 1], qa[hh * 8 + 2], qa[hh * 8 + 3], b[0], b[1]);
            }
          if (h == 0) PUMPN()
          PROFH(6, 18);
          float va[2][2], vb[2][2], mx[2][2];
#pragma unroll
          for (int hh = 0; hh < 2; hh++) {
            va[hh][0] = gt0 ? s[hh][0][0] : s[hh][1][0];
            vb[hh][0] = gt1 ? s[hh][0][1] : s[hh][1][1];
            va[hh][1] = gt0 ? s[hh][1][2] : s[hh][2][2];
            vb[hh][1] = gt1 ? s[hh][1][3] : s[hh][2][3];
          }
          if (warp < 2 && mm == 0) {
#pragma unroll
            for (int hh = 0; hh < 2; hh++) { if (gt0) va[hh][0] = -INFINITY; if (gt1) vb[hh][0] = -INFINITY; }
          }
#pragma unroll
          for (int i = 0; i < 4; i++) mx[i >> 1][i & 1] = fmaxf(va[i >> 1][i & 1], vb[i >> 1][i & 1]);
#pragma unroll
          for (int o = 1; o <= 2; o <<= 1)
#pragma unroll
            for (int i = 0; i < 4; i++) mx[i >> 1][i & 1] = fmaxf(mx[i >> 1][i & 1], __shfl_xor_sync(0xffffffffu, mx[i >> 1][i & 1], o));
          const float sc0 = rs0 * (0.17677669529663687f * LOG2E), sc1 = rs1 * (0.17677669529663687f * LOG2E);
#pragma unroll
          for (int i = 0; i < 4; i++) {
            const float sc = (i & 1) ? sc1 : sc0, m = mx[i >> 1][i & 1];
            va[i >> 1][i & 1] = ex2((va[i >> 1][i & 1] - m) * sc); vb[i >> 1][i & 1] = ex2((vb[i >> 1][i & 1] - m) * sc);
            mx[i >> 1][i & 1] = va[i >> 1][i & 1] + vb[i >> 1][i & 1];
          }
          if (h == 0) { PIN(&va[0][0], 4); PIN(&vb[0][0], 4); PIN(&mx[0][0], 4); PUMP1(); }
          if (h) PROF(20);
          if (warp < 2) mbar_wait(bar_halo + 8, h);
          if (h) PROF(21);
          if (h == 0) mbar_wait(ub, par);
          FRAG_GET(vf, 1);
#pragma unroll
          for (int o = 1; o <= 2; o <<= 1)
#pragma unroll
            for (int i = 0; i < 4; i++) mx[i >> 1][i & 1] += __shfl_xor_sync(0xffffffffu, mx[i >> 1][i & 1], o);
          float o[8][4];
          uint32_t pa[4][2];
#pragma unroll
          for (int i = 0; i < 4; i++) {
            const float iv = rcp_fast(mx[i >> 1][i & 1]);
            const uint32_t w = pack_bf16(va[i >> 1][i & 1] * iv, vb[i >> 1][i & 1] * iv);
            pa[i][0] = w & msk[0]; pa[i][1] = w & ~msk[0];
          }
          PROFH(7, 19);
#pragma unroll
          for (int i = 7; i >= 0; i--) {
            const uint32_t* a = vf + (i >> 2) * 8 + (i & 3) * 2;
            mma_bf16_z(o[i], a[0], a[1], a[8], a[9], pa[(i & 2) + (i >> 2)][0], pa[(i & 2) + (i >> 2)][1]);
          }
          if (h == 0) PUMPN() else mbar_wait(bar_done + 30 * 8, par);
          if (NLAYERS > 1 && l + h == 0) mbar_wait(bar_phi + 8, 0);
          if (h) PROF(22);
          {
            const uint32_t pm0 = msk[1], pbit = O_BIT(l) * 0x10001u;
#pragma unroll
            for (int i = 0; i < 4; i++)
              stsm_x4_t(ta[i] + (h ? 3 : 12) * SLOT, PBIT(pack_bf16(o[i][0], o[i][1])), PBIT(pack_bf16(o[i + 4][0], o[i + 4][1])),
                        pack_bf16(o[i][2], o[i][3]), pack_bf16(o[i + 4][2], o[i + 4][3]));
          }
          WARP_STORE(&tm_os, sbase + (h ? 3 : 12) * SLOT, jj * 128 + h * 64, mm * 128);
          PROFH(11, 23);
          if (h) break;
          REST_P1(ASKEW);
          asm volatile("cp.async.bulk.wait_group.read 0;" ::: "memory");
          DRAIN_A(S1, 1, {});
        }
      } else {
        constexpr uint32_t par = 1;
        float st[32];
        const float c0 = rs0 * LOG2E, c1 = rs1 * LOG2E;
        { V_ADDR(pV, 0); STAGE_V(S0 + 64); }
        if (warp < 2) sts128(sbase + OFF_ONES + warp * 512 + lane * 16, 0x3F803F80u, 0x3F803F80u, 0x3F803F80u, 0x3F803F80u);
        scale32(st, S0, c0, c1);
        PIN(st, 32);
#define PHI_PIECE(c) { \
          e_[2 * (c)] = ex2(st[2 * (c)]); e_[2 * (c) + 1] = ex2(st[2 * (c) + 1]); \
          _Pragma("unroll") for (int k_ = 4 * (c); k_ < 4 * (c) + 4; k_++) m_[(c) >> 1] = (k_ & 7) ? fmaf(st[k_], st[k_], m_[(c) >> 1]) : st[k_] * st[k_]; \
          asm volatile("" : "+f"(e_[2 * (c)]), "+f"(e_[2 * (c) + 1]), "+f"(m_[(c) >> 1])); SCHED_FENCE(); }
#define PHI_FIN() { \
          big = __any_sync(0xffffffffu, !(fmaxf(fmaxf(m_[0], m_[1]), fmaxf(m_[2], m_[3])) < BIGLIM)); \
          if (__builtin_expect(big, 0)) { COPYN(e_, st, 16); } \
          _Pragma("unroll") for (int k_ = 0; k_ < 16; k_++) st[k_] = e_[k_]; \
          PIN(st, 16); }
#define KV_MMA(vs, IL) { \
          const uint32_t dp = dA0 + 12 * 1024 - wg * 2560, dv = dA0 + (vs) * 1024 + ((OFF_ONES - (vs) * SLOT - 16) << 12) - wg * (512 << 16); \
          STG_WAIT(); \
          fence_proxy_async_smem(); \
          wgmma_fence(); \
          _Pragma("unroll") for (int ks = 0; ks < 8; ks++) { \
            const uint64_t a = DESC(dp + ks * 128, 0x40000040), b = DESC(dv + ks * (64 - (64 << 16)), 0x80000020); \
            if ((IL) && ks) wgmma_fence(); \
            if (ks == 0) wgmma_n40<0, 1>(kv, a, b); else wgmma_n40<1, 1>(kv, a, b); \
            if (ks == 7) wgmma_commit(); \
            if (IL) PHI_PIECE(ks); } }
#define KV_RED1(i) if (h) red_v4(g_kv[l >> 1] + (jj * 4) * KVH + warp * 768 + lane * 4 + (i) * 128, S0[32 + (i) * 3], S0[33 + (i) * 3], S0[34 + (i) * 3], 1.f)
#define KV_REDS(n) { _Pragma("unroll") for (int i_ = 0; i_ < 6; i_++) if (((RPACE >> (4 * i_)) & 15) == (n)) KV_RED1(i_); }
#define KV_SEND(kp) { \
          float sd[9]; \
          _Pragma("unroll") for (int i = 0; i < 8; i++) { (kp)[i] = kv[i]; sd[i] = kv[8 + i]; } \
          (kp)[8] = rank ? kv[18] : kv[16]; sd[8] = rank ? kv[16] : kv[18]; \
          const uint32_t ra = sbase + peer + (warp * 32 + lane) * 4, rb = bar_kx + peer; \
          if (elect_one()) mbar_expect_tx(bar_kx, 1152); \
          _Pragma("unroll") for (int i = 0; i < 2; i++) \
            asm volatile("st.async.weak.shared::cluster.mbarrier::complete_tx::bytes.v4.f32 [%0], {%1, %2, %3, %4}, [%5];" \
                         :: "r"(ra + (warp * 32 + lane) * 12 + OFF_PHI + i * 4096), "f"(sd[4 * i]), "f"(sd[4 * i + 1]), "f"(sd[4 * i + 2]), "f"(sd[4 * i + 3]), "r"(rb) : "memory"); \
          asm volatile("st.async.weak.shared::cluster.mbarrier::complete_tx::bytes.f32 [%0], %1, [%2];" :: "r"(ra + OFF_LNB), "f"(sd[8]), "r"(rb) : "memory"); }
#define KV_RECV(kp, hp) { \
          float r_[9]; \
          float* kvg = g_kv[l >> 1] + (jj * 4 + (hp) * 2) * KVH + warp * 768 + rank * 384 + lane * 4; \
          mbar_wait(bar_kx, l >> 1); \
          _Pragma("unroll") for (int i = 0; i < 2; i++) \
            asm volatile("ld.shared.v4.f32 {%0, %1, %2, %3}, [%4];" : "=f"(r_[4 * i]), "=f"(r_[4 * i + 1]), "=f"(r_[4 * i + 2]), "=f"(r_[4 * i + 3]) \
                         : "r"(sbase + OFF_PHI + i * 4096 + (warp * 32 + lane) * 16) : "memory"); \
          r_[8] = lds32f(sbase + OFF_LNB + (warp * 32 + lane) * 4); \
          _Pragma("unroll") for (int i = 0; i < 3; i++) red_v4(kvg + i * 128, (kp)[3 * i] + r_[3 * i], (kp)[3 * i + 1] + r_[3 * i + 1], (kp)[3 * i + 2] + r_[3 * i + 2], 2.f); }
#define KV_LOAD(hp) { \
          const uint4* kvg = reinterpret_cast<const uint4*>(g_kv[l >> 1] + (jj * 4 + (hp) * 2) * KVH) + warp * 192 + lane; \
          _Pragma("unroll") for (int i = 0; i < 6; i++) v[i] = ld_b128(kvg + i * 32); }
#define KVV(i) __uint_as_float((i) % 3 == 0 ? v[(i) / 3].x : ((i) % 3 == 1 ? v[(i) / 3].y : v[(i) / 3].z))
#define KV_TILE(hp) { \
          _Pragma("unroll 1") for (int it = 0; it < (1 << 16); it++) { \
            if (__all_sync(0xffffffffu, (v[0].w & v[1].w & v[2].w & v[3].w & v[4].w & v[5].w) == 0x41800000u)) break; \
            RETRY_COUNT(); \
            KV_LOAD(hp); \
          } \
          if (hp) PROF(26); else PROF(25); \
          const uint32_t e = lane & 7, jt = ((lane >> 1) & 4) + (e >> 1); \
          const uint32_t row = ((((warp >> 1) ^ wg) & 1) << 5) + ((jt & 1) << 4) + ((warp & 1) << 3) + (jt & 6) + (e & 1); \
          const uint32_t kd = pV + wg * 8192 + row * 128, ksw = (row & 7) << 4; \
          _Pragma("unroll") for (int i = 0; i < 2; i++) \
            stsm_x4(kd + ((i * 32 + lhi) ^ ksw), pack_bf16(KVV(i * 9), KVV(i * 9 + 1)), pack_bf16(KVV(i * 9 + 2), KVV(i * 9 + 3)), \
                    pack_bf16(KVV(i * 9 + 4), KVV(i * 9 + 5)), pack_bf16(KVV(i * 9 + 6), KVV(i * 9 + 7))); \
          stsm_x4(kd + ((64u + lhi) ^ ksw), pack_bf16(KVV(8), 1.f), pack_bf16(KVV(17), 1.f), 0u, 0u); }
#pragma unroll 1
        for (int h = 0; h < 2; h++) {
          PROFH(4, 6);
          PUMP0();
          LANE_CONSTS();
          const uint32_t dsw = (uint32_t)(g ^ (2 * t)) << 4, dst = ((t & 2) ? pK : sbase + 12 * SLOT) + (r0 + g) * 128;
          float e[16], f[16];
          KV_REDS(1);
          float sa = exps16_<0>(e, st);
          exps16_fix<0>(e, st, sa);
          asm volatile("" : "+f"(sa)); PIN(e, 16); PUMP0();
          if (h) STG_WAIT();
          KV_REDS(2);
          store16(e, sa, dst, dsw, 4);
          float sb = exps16_<1>(f, st);
          exps16_fix<1>(f, st, sb);
          asm volatile("" : "+f"(sb)); PIN(f, 16); PUMP0();
          KV_REDS(3);
          store16(f, sb, dst, dsw, 0);
          float sc = exps16_<0>(e, st + 2);
          exps16_fix<0>(e, st + 2, sc);
          asm volatile("" : "+f"(sc)); PIN(e, 16); PUMP0();
          KV_REDS(4);
          store16(e, sc, dst + 1024, dsw, 4);
          float sd = exps16_<1>(f, st + 2);
          exps16_fix<1>(f, st + 2, sd);
          asm volatile("" : "+f"(sd)); PIN(f, 16); PUMP0();
          store16(f, sd, dst + 1024, dsw, 0);
          PROFH(5, 7);
          if (h) break;
          {
            float kv[20];
            ACC_DEF(kv, 20);
            STG_ARRIVE();
            float e_[16], m_[4];
            KV_MMA(11, 0);
            PUMP0();
            ACC_FENCE(kv, 20);
            STG_ARRIVE();
            scale32(st, S0 + 32, c0, c1);
            PIN(st, 32);
            {
              COPYN(S0 + 32, kv, 8); COPYN(S0 + 40, kv + 16, 1); COPYN(S0 + 41, kv + 8, 8); COPYN(S0 + 49, kv + 18, 1);
              const int h = 1;
              KV_REDS(0);
            }
          }
        }
        bool big;
        uint4 v[6];
        {
          float kv[20];
          { LANE_CONSTS(); KV_LOAD(0); }
          mbar_wait(bar_stat2, par);
          ub = bar_full + 240;
          LNSTEP(S1, 1);
          PUMP1();
          if (wg == 0) bar_sync<BAR_SKEW, 256>();
          QSTEP(S1, RA_CUR, 1);
          if (wg == 1) bar_arrive<BAR_SKEW, 256>();
          QREL();
          { LANE_CONSTS(); KV_TILE(0); }
          LANE_CONSTS();
          V_ADDR(sbase + 3 * SLOT, rank * 32);
          PINU(va_, 2);
          mbar_wait(bar_done + 30 * 8, par);
          wgmma_wait<0>();
          ACC_FENCE(S1, 96);
          PROF(13);
          STAGE_V(S1 + 64);
          STG_ARRIVE();
          REL(bar_done + 31 * 8);
          scale32(st, S1, c0, c1);
          PIN(st, 32);
          PROF(16);
          ACC_DEF(kv, 20);
          float e_[16], m_[4];
          KV_MMA(3, 1);
          SCHED_FENCE();
          PROF(14);
          PHI_FIN();
          SCHED_FENCE();
          PROF(15);
          wgmma_wait<0>();
          ACC_FENCE(kv, 20);
          PROF(12);
          { float kp[9]; KV_SEND(kp); _Pragma("unroll") for (int i = 0; i < 3; i++) v[i] = make_uint4(__float_as_uint(kp[3 * i]), __float_as_uint(kp[3 * i + 1]), __float_as_uint(kp[3 * i + 2]), 0u); }
#define VDEF(i0) _Pragma("unroll") for (int i = (i0); i < 6; i++) asm volatile("" : "=r"(v[i].x), "=r"(v[i].y), "=r"(v[i].z), "=r"(v[i].w))
          VDEF(3);
          PROF(17);
        }
#pragma unroll 1
        for (int h = 0; h < 2; h++) {
          const uint32_t pO = sbase + (h ? 3 : 8) * SLOT;
          LANE_CONSTS();
          uint32_t fq[32];
          if (h) { KV_LOAD(1); phiq_a(st, big); PIN(st, 16); PROF(31); }
          PROFH(18, 32);
          SCHED_FENCE();
          phiq_b<1>(fq, st, big); PINU(fq, 16); PIN(st + 16, 16);
          SCHED_FENCE();
          PROFH(8, 9);
          if (h) {
            asm volatile("cp.async.bulk.wait_group.read 0;" ::: "memory");
            mbar_wait(bar_lx, par);
            PROF(30);
            KV_TILE(1);
            STG_ARRIVE();
          }
          SCHED_FENCE();
          if (h == 0) {
            float kp[9];
#pragma unroll
            for (int i = 0; i < 9; i++) kp[i] = KVV(i);
            KV_RECV(kp, 1);
            SCHED_FENCE();
          }
          phiq_b<0>(fq + 16, st + 16, big); PINU(fq + 16, 16);
          PROFH(10, 21);
          if (h) { STG_WAIT(); fence_proxy_async_smem(); }
          wgmma_wait<0>();
          ACC_FENCE(S1, 64);
          PROFH(19, 33);
          float o[4][20];
#define O_MMA(hh) { \
            const uint64_t db = make_desc(pV + (hh) * 8192, 16, 1024); \
            ACC_DEF(o[(hh) * 2], 20); ACC_DEF(o[(hh) * 2 + 1], 20); \
            wgmma_fence(); \
            wgmma_n40_rs<0>(o[(hh) * 2], fq + (hh) * 16, db + 256); wgmma_n40_rs<0>(o[(hh) * 2 + 1], fq + (hh) * 16 + 8, db); \
            wgmma_n40_rs<1>(o[(hh) * 2], fq + (hh) * 16 + 4, db + 384); wgmma_n40_rs<1>(o[(hh) * 2 + 1], fq + (hh) * 16 + 12, db + 128); \
            wgmma_commit(); }
          O_MMA(0);
          SCHED_FENCE();
          PMASKS(true, O_BIT(l));
#pragma unroll
          for (int hh = 0; hh < 2; hh++) {
            wgmma_wait<0>();
            ACC_FENCE(o[hh * 2], 20); ACC_FENCE(o[hh * 2 + 1], 20);
            if (!hh) { O_MMA(1); SCHED_FENCE(); }
            if (hh) PROFH(22, 24);
            const float* x = o[hh * 2];
            const float* y = o[hh * 2 + 1];
            const float sx0 = x[17] * 0x1p-40f, sy0 = y[17] * 0x1p-40f, sx1 = x[19] * 0x1p-40f, sy1 = y[19] * 0x1p-40f;
            const float i0 = rcp_fast(fmaf(fmaf(x[17], 1e-6f, x[16]), sy0, y[16] * sx0)), i1 = rcp_fast(fmaf(fmaf(x[19], 1e-6f, x[18]), sy1, y[18] * sx1));
            const float ax0 = sy0 * i0, ay0 = sx0 * i0, ax1 = sy1 * i1, ay1 = sx1 * i1;
#pragma unroll
            for (int dp = 0; dp < 2; dp++)
              stsm_x4(pO + srowoff + ((hh * 64 + dp * 32 + lhi) ^ lsw),
                      PBIT(pack_bf16(fmaf(x[dp * 8], ax0, y[dp * 8] * ay0), fmaf(x[dp * 8 + 1], ax0, y[dp * 8 + 1] * ay0))),
                      PBIT(pack_bf16(fmaf(x[dp * 8 + 2], ax1, y[dp * 8 + 2] * ay1), fmaf(x[dp * 8 + 3], ax1, y[dp * 8 + 3] * ay1))),
                      (pack_bf16(fmaf(x[dp * 8 + 4], ax0, y[dp * 8 + 4] * ay0), fmaf(x[dp * 8 + 5], ax0, y[dp * 8 + 5] * ay0))),
                      (pack_bf16(fmaf(x[dp * 8 + 6], ax1, y[dp * 8 + 6] * ay1), fmaf(x[dp * 8 + 7], ax1, y[dp * 8 + 7] * ay1))));
          }
          WARP_STORE(&tm_os, pO, jj * 128 + h * 64, mm * 128);
          PROFH(20, 34);
          if (h) break;
          float T_[64];
          scale32(st, S1 + 32, c0, c1);
          PIN(st, 32);
          ACC_DEF(T_, 64);
          XM_ISSUE(); wgmma_commit();
          SCHED_FENCE();
          big = any_big(st);
          SCHED_FENCE();
          PROF(27);
          wgmma_wait<0>(); XM_DONE();
          PROF(28);
          bar_wg(wg);
          WSTEP();
          SCHED_FENCE();
          VDEF(0);
          PROF(29);
        }
      }
      __syncwarp();
      if (elect_one()) mbar_arrive_local(bar_epi);
      bar_wg(wg);
#pragma unroll 1
      while (ub < bar_full + 384) {
        WSTEP();
        if (ub == bar_full + 8 * 41) { asm volatile("cp.async.bulk.wait_group.read 0;" ::: "memory"); PROF(35); }
        if (ub == bar_full + 8 * 42) PROF(36);
      }
      {
        float Wb[32];
        LANE_CONSTS();
        TILE_CONSTS(pK, l < NLAYERS - 1, X_BIT(l));
        if (l < NLAYERS - 1) mbar_wait(bar_full, par ^ 1);
        wgmma_wait<0>();
        ACC_FENCE(S1, 64);
        COPYN(Wb, S1 + 32, 32);
        PROF(37);
        uint32_t xa[16];
#pragma unroll
        for (int i = 0; i < 16; i++) { const uint32_t w = pack_bf16(S1[2 * i], S1[2 * i + 1]); xa[i] = (i & 2) ? w : PBIT(w); }
        PINU(xa, 16);
#define XA_OUT() _Pragma("unroll") for (int j = 0; j < 4; j++) stsm_x4(ta[j], xa[4 * j], xa[4 * j + 1], xa[4 * j + 2], xa[4 * j + 3])
        if (l == NLAYERS - 1) {
          XA_OUT();
          int w; asm volatile("mov.u32 %0, %1;" : "=r"(w) : "r"(warp));
          const int oc = jj * 128 + (w & 1) * 1024, orow = mm * 64 + (w >> 1) * 16 - r0;
          WARP_STORE(&tm_xo, pK, oc, orow);
          { PMASKS(false, 0); X_OUT(1, Wb); }
          WARP_STORE(&tm_xo, pV, oc + 64, orow);
          break;
        }
        PROF(38);
        XA_OUT();
        ACC_DEF(S0, 96);
        wgmma_fence();
        wgmma_n192_rs<0>(S0, xa, dB0);
#pragma unroll
        for (int k = 1; k < RSK; k++) wgmma_n192_rs<1>(S0, xa + 4 * k, dB0 + 128 * k);
        wgmma_commit();
        WARP_STORE(&tm_os, pK, jj * 128, mm * 128 + S_LEN);
        if (RSK < 4) {
          wgmma_fence();
#pragma unroll
          for (int k = RSK; k < 4; k++) wgmma_n192_rs<1>(S0, xa + 4 * k, dB0 + 128 * k);
          wgmma_commit();
        }
        { const int ln_ = l + 1, l = ln_; const uint32_t ub = bar_full; (void)l; (void)ub; PROFS(); }
        REL(bar_done + 47 * 8);
        PROF(39);
        { PMASKS(false, 0); X_OUT(1, Wb); }
        fence_proxy_async_smem();
      }
    }
    asm volatile("cp.async.bulk.wait_group.read 0;" ::: "memory");
    cluster_sync();
  }
}

typedef CUresult (*PFN_encode)(CUtensorMap*, CUtensorMapDataType, cuuint32_t, void*, const cuuint64_t*, const cuuint64_t*,
                               const cuuint32_t*, const cuuint32_t*, CUtensorMapInterleave, CUtensorMapSwizzle,
                               CUtensorMapL2promotion, CUtensorMapFloatOOBfill);

CUtensorMap make_map(PFN_encode enc, const void* ptr, uint64_t inner, uint64_t outer, uint32_t box_inner, uint32_t box_outer,
                     CUtensorMapSwizzle swz = CU_TENSOR_MAP_SWIZZLE_128B, int promo = CU_TENSOR_MAP_L2_PROMOTION_L2_256B) {
  CUtensorMap m;
  cuuint64_t dims[2] = {inner, outer};
  cuuint64_t strides[1] = {inner * 2};
  cuuint32_t box[2] = {box_inner, box_outer};
  cuuint32_t es[2] = {1, 1};
  enc(&m, CU_TENSOR_MAP_DATA_TYPE_BFLOAT16, 2, const_cast<void*>(ptr), dims, strides, box, es, CU_TENSOR_MAP_INTERLEAVE_NONE,
      swz, (CUtensorMapL2promotion)promo, CU_TENSOR_MAP_FLOAT_OOB_FILL_NONE);
  return m;
}

CUtensorMap make_tile_map(PFN_encode enc, const void* ptr, uint64_t rows, bool by_parity, int promo) {
  CUtensorMap m;
  cuuint64_t dims[4] = {D_MODEL, 16, 2, rows / 32};
  cuuint64_t strides[3] = {by_parity ? 4096u : 2048u, by_parity ? 2048u : 32768u, 65536};
  cuuint32_t box[4] = {64, 16, 2, 4};
  cuuint32_t es[4] = {1, 1, 1, 1};
  enc(&m, CU_TENSOR_MAP_DATA_TYPE_BFLOAT16, 4, const_cast<void*>(ptr), dims, strides, box, es, CU_TENSOR_MAP_INTERLEAVE_NONE,
      CU_TENSOR_MAP_SWIZZLE_128B, (CUtensorMapL2promotion)promo, CU_TENSOR_MAP_FLOAT_OOB_FILL_NONE);
  return m;
}

}

extern "C" void kernel_launch(void* const* d_in, const int* in_sizes, int n_in, void* d_out, int out_size) {
  (void)in_sizes; (void)n_in; (void)out_size;
  static PFN_encode enc = nullptr;
  if (!enc) {
    void* fn = nullptr;
    cudaDriverEntryPointQueryResult qr;
    cudaGetDriverEntryPoint("cuTensorMapEncodeTiled", &fn, cudaEnableDefault, &qr);
    enc = (PFN_encode)fn;
    cudaFuncSetAttribute(mega_kernel, cudaFuncAttributeMaxDynamicSharedMemorySize, SMEM_BYTES);
  }
  Params prm;
  prm.x0 = (const __nv_bfloat16*)d_in[0];
  prm.wA_qkv = (const __nv_bfloat16*)d_in[1];
  prm.wA_o = (const __nv_bfloat16*)d_in[2];
  prm.wB_qkv = (const __nv_bfloat16*)d_in[4];
  prm.wB_phi = (const __nv_bfloat16*)d_in[5];
  prm.wB_o = (const __nv_bfloat16*)d_in[6];
  prm.out = (__nv_bfloat16*)d_out;
  void *obuf = nullptr, *wf = nullptr;
  cudaGetSymbolAddress(&obuf, g_obuf);
  cudaGetSymbolAddress(&wf, g_wfold);
  CUtensorMap tm_x0 = make_tile_map(enc, d_in[0], S_LEN, true, XPROMO);
  CUtensorMap tm_xo = make_map(enc, d_out, 2 * D_MODEL, S_LEN / 2, 64, 16);
  CUtensorMap tm_os = make_map(enc, obuf, D_MODEL, 2 * S_LEN, 64, 16);
  CUtensorMap tm_o = make_tile_map(enc, obuf, 2 * S_LEN, false, OPROMO);
  CUtensorMap tm_wf = make_map(enc, wf, 2048, D_MODEL, 64, 32);
  CUtensorMap tm_wqA = make_map(enc, d_in[1], 3 * D_MODEL, D_MODEL, 64, 32, CU_TENSOR_MAP_SWIZZLE_128B, WPROMO);
  CUtensorMap tm_wqB = make_map(enc, prm.wB_qkv, 3 * D_MODEL, D_MODEL, 64, 32);
  CUtensorMap tm_woA = make_map(enc, prm.wA_o, D_MODEL, D_MODEL, 64, 64);
  CUtensorMap tm_woB = make_map(enc, prm.wB_o, D_MODEL, D_MODEL, 64, 64);
  CUtensorMap tm_phi = make_map(enc, prm.wB_phi, 32, 1024, 32, 128, CU_TENSOR_MAP_SWIZZLE_64B);
  mega_kernel<<<NMAIN + NAUX, 384, SMEM_BYTES>>>(tm_x0, tm_xo, tm_os, tm_o, tm_wf, tm_wqA, tm_wqB, tm_woA, tm_woB, tm_phi, prm);
}
```

```cpp
#include <cuda_runtime.h>
#include <cuda.h>
#include <cuda_bf16.h>
#include <stdint.h>

#define NLAYERS 4

#define HPUMP2 1
#define ASKEW 2
#define FPUMP 3
#define PFGAP 100
#define POLLGAP 120
#define HW1 30
#define XPACE 0x06050401000000ull
#define HW0 18
#define XD 4
#define WFGAP 50
#define EARLY 4
#define BIGLIM 3600.f
#define SUMLO 0x1p-100f
#define SUMHI 0x1p100f
#define XPROMO 2
#define OPROMO 3
#define STAG2 0
#define WPROMO 3
#define SB0 2
#define SB1 4
#define SB2 6
#define PROWS 7
#define SPD0 0
#define SPD1 0
#define SPD2 300
#define FRB 0x3535353535ull
#define NOB 0xFFFFFF00u
#define NO1 ~0u
#define NOX ~0u
#define FD0 3
#define XP0 0
#define CSGAP 300
#define AUXORD 0x76543210
#define OWNW0 1
#define OWNW1 2
#define RPACE 0x221100
#define RSK 2
namespace {

constexpr int S_LEN = 2048, D_MODEL = 1024;
constexpr int NAUX = 4, NMAIN = 128;
constexpr int SLOT = 16384;
constexpr int QST = 24576;
constexpr int OFF_RA = 6 * SLOT, OFF_S = 10 * SLOT;
constexpr int OFF_HALO = 13 * SLOT, OFF_LNB = OFF_HALO  , OFF_ONES = OFF_HALO + 3072;
constexpr int OFF_ST = OFF_HALO + 7168  , OFF_ID = OFF_HALO + 7680, OFF_PHI = OFF_HALO + 8192;
constexpr int OFF_BAR = 14 * SLOT;
constexpr int OFF_LNA = OFF_BAR + 1024;
constexpr int SMEM_BYTES = OFF_LNA + 2048;
#define WO_ASLOT(par) ((par) ? 0x9876CAB39876CA98ull : 0xBC7698A3BC7698BCull)
constexpr unsigned long long WO_BSLOT = 0x5432105421054210ull;
__device__ __forceinline__ int srcb(int j, int i) { return (i + (i >= j)) & 7; }
__device__ __forceinline__ int kslice(int j, int i) { return i < 2 ? 2 * j + i : (i < 9 ? 2 * srcb(j, i - 2) : 2 * srcb(j, i - 9) + 1); }
__device__ __forceinline__ int wslice(int j, int s) { return 2 * ((s & 7) ? srcb(j, (s & 7) - 1) : j) + (s >> 3); }
constexpr int KVH = 6 * 128 * 4;

struct __align__(128) Flag { unsigned v; unsigned pad[31]; };
struct Flags {
  Flag xready[4][16];
  Flag wfready[8];
  Flag done;
  Flag epoch;
};

__device__ Flags g_flags;
__device__ __nv_bfloat16 g_obuf[2 * S_LEN * D_MODEL];
#define O_BIT(l) ((epoch * NLAYERS + (l) + 1) & 1u)
#define X_BIT(l) ((epoch * (NLAYERS - 1) + (l) + 1) & 1u)
__device__ __nv_bfloat16 g_wfold[D_MODEL * 2048];
__device__ uint4 g_halo[16 * 8 * 512];
__device__ __align__(128) float g_kv[2][32 * KVH];
__device__ __align__(128) uint2 g_colsum[2][1536][2];
__device__ __align__(128) uint2 g_stats[S_LEN * 8];
#define H_BIT(l) (NLAYERS > 2 ? (uint32_t)((l) == 0) : (ep1 & 1))
#define STAT_TAG(l) ((ep1 * NLAYERS + (l) + 1) & 3u)

#define RETRY_COUNT()
#define PRL 3
#define PROFL 1
#define PROFW 0
#define PROFT(i) do {} while (0)
#define PROF(i) do {} while (0)
#define PROFH(i, j) do {} while (0)
#define PROFL3(i) do {} while (0)

__device__ __forceinline__ uint32_t smem_u32(const void* p) { return (uint32_t)__cvta_generic_to_shared(p); }
__device__ __forceinline__ bool elect_one() {
  uint32_t p;
  asm volatile("{\n.reg .pred p;\nelect.sync _|p, 0xffffffff;\nselp.u32 %0, 1, 0, p;\n}\n" : "=r"(p));
  return p != 0;
}
__device__ __forceinline__ void mbar_init(uint32_t bar, uint32_t cnt) {
  asm volatile("mbarrier.init.shared::cta.b64 [%0], %1;" :: "r"(bar), "r"(cnt));
}
__device__ __forceinline__ void mbar_expect_tx(uint32_t bar, uint32_t bytes) {
  asm volatile("mbarrier.arrive.expect_tx.shared::cta.b64 _, [%0], %1;" :: "r"(bar), "r"(bytes) : "memory");
}
#define mbar_wait(bar, parity) \
  asm volatile("{\n.reg .pred p, q;\nW_%=:\nmbarrier.try_wait.parity.shared::cta.b64 p, [%1], %2;\nadd.s32 %0, %0, -1;\n" \
               "setp.gt.and.s32 q, %0, 0, !p;\n@q bra.uni W_%=;\n}\n" : "+r"(budget) : "r"((uint32_t)(bar)), "r"((uint32_t)(parity)) : "memory")
#define mbar_wait_sl(bar, parity) \
  asm volatile("{\n.reg .pred p, q;\nW_%=:\nmbarrier.try_wait.parity.shared::cta.b64 p, [%1], %2, 20000;\nadd.s32 %0, %0, -64;\n" \
               "setp.gt.and.s32 q, %0, 0, !p;\n@q bra.uni W_%=;\n}\n" : "+r"(budget) : "r"((uint32_t)(bar)), "r"((uint32_t)(parity)) : "memory")
__device__ __forceinline__ void mbar_arrive_local(uint32_t bar) {
  asm volatile("mbarrier.arrive.shared::cta.b64 _, [%0];" :: "r"(bar) : "memory");
}
__device__ __forceinline__ void tma_load_2d(uint32_t dst, const CUtensorMap* tm, uint32_t bar, int c0, int c1) {
  asm volatile("cp.async.bulk.tensor.2d.shared::cluster.global.mbarrier::complete_tx::bytes [%0], [%1, {%3, %4}], [%2];"
               :: "r"(dst), "l"(tm), "r"(bar), "r"(c0), "r"(c1) : "memory");
}
__device__ __forceinline__ void tma_load_2d_mc(uint32_t dst, const CUtensorMap* tm, uint32_t bar, int c0, int c1) {
  asm volatile("cp.async.bulk.tensor.2d.shared::cluster.global.mbarrier::complete_tx::bytes.multicast::cluster [%0], [%1, {%3, %4}], [%2], %5;"
               :: "r"(dst), "l"(tm), "r"(bar), "r"(c0), "r"(c1), "h"((uint16_t)3) : "memory");
}
__device__ __forceinline__ void tma_store_2d(const CUtensorMap* tm, uint32_t src, int c0, int c1) {
  asm volatile("cp.async.bulk.tensor.2d.global.shared::cta.bulk_group [%0, {%2, %3}], [%1];"
               :: "l"(tm), "r"(src), "r"(c0), "r"(c1) : "memory");
}
__device__ __forceinline__ void tma_load_t(uint32_t dst, const CUtensorMap* tm, uint32_t bar, int c0, int row) {
  asm volatile("cp.async.bulk.tensor.4d.shared::cluster.global.mbarrier::complete_tx::bytes [%0], [%1, {%3, %5, %5, %4}], [%2];"
               :: "r"(dst), "l"(tm), "r"(bar), "r"(c0), "r"(row >> 5), "r"(0) : "memory");
}
__device__ __forceinline__ void tma_store_t(const CUtensorMap* tm, uint32_t src, int c0, int row) {
  asm volatile("cp.async.bulk.tensor.4d.global.shared::cta.bulk_group [%0, {%2, %4, %4, %3}], [%1];"
               :: "l"(tm), "r"(src), "r"(c0), "r"(row >> 5), "r"(0) : "memory");
}
__device__ __forceinline__ void bulk_commit_wait() {
  asm volatile("cp.async.bulk.commit_group;\ncp.async.bulk.wait_group 0;" ::: "memory");
}
__device__ __forceinline__ void prefetch_tmap(const CUtensorMap* tm) {
  asm volatile("prefetch.tensormap [%0];" :: "l"(tm) : "memory");
}
__device__ __forceinline__ void fence_proxy_async_global() { asm volatile("fence.proxy.async.global;" ::: "memory"); }
__device__ __forceinline__ void fence_proxy_async_smem() { asm volatile("fence.proxy.async.shared::cta;" ::: "memory"); }
__device__ __forceinline__ unsigned ld_relaxed(const unsigned* p) {
  unsigned v;
  asm volatile("ld.relaxed.gpu.global.u32 %0, [%1];" : "=r"(v) : "l"(p) : "memory");
  return v;
}
__device__ __forceinline__ void fence_acquire() { asm volatile("fence.acquire.gpu;" ::: "memory"); }
__device__ __forceinline__ void wait_flag(const unsigned* p, unsigned target) {
  int it = 0;
  while ((int)(ld_relaxed(p) - target) < 0 && ++it < (1 << 20)) {}
  fence_acquire();
}
__device__ __forceinline__ void signal_release(unsigned* p) {
  asm volatile("red.release.gpu.global.add.u32 [%0], 1;" :: "l"(p) : "memory");
}
template <int ID, int N> __device__ __forceinline__ void bar_arrive() { asm volatile("bar.arrive %0, %1;" :: "n"(ID), "n"(N) : "memory"); }
template <int ID, int N> __device__ __forceinline__ void bar_sync() { asm volatile("bar.sync %0, %1;" :: "n"(ID), "n"(N) : "memory"); }
__device__ __forceinline__ void bar_wg(int wg) { asm volatile("bar.sync %0, 128;" :: "r"(2 + wg) : "memory"); }
__device__ __forceinline__ void cluster_sync() {
  asm volatile("barrier.cluster.arrive.relaxed.aligned;\nbarrier.cluster.wait.aligned;" ::: "memory");
}
__device__ __forceinline__ void cluster_wait() { asm volatile("barrier.cluster.wait.acquire.aligned;" ::: "memory"); }
enum { BAR_X1 = 7, BAR_WF = 8  , BAR_SKEW = 10 };

__device__ __forceinline__ void wgmma_fence() { asm volatile("wgmma.fence.sync.aligned;" ::: "memory"); }
__device__ __forceinline__ void wgmma_commit() { asm volatile("wgmma.commit_group.sync.aligned;" ::: "memory"); }
template <int N> __device__ __forceinline__ void wgmma_wait() { asm volatile("wgmma.wait_group.sync.aligned %0;" :: "n"(N) : "memory"); }

template <int scale_d, int tnsp_b = 1> __device__ __forceinline__ void wgmma_n192(float* d, uint64_t descA, uint64_t descB) {
  asm volatile("{\n.reg .pred p;\nsetp.ne.b32 p, %98, 0;\n"
               "wgmma.mma_async.sync.aligned.m64n192k16.f32.bf16.bf16 {%0,%1,%2,%3,%4,%5,%6,%7,%8,%9,%10,%11,%12,%13,%14,%15,%16,%17,%18,%19,%20,%21,%22,%23,%24,%25,%26,%27,%28,%29,%30,%31,%32,%33,%34,%35,%36,%37,%38,%39,%40,%41,%42,%43,%44,%45,%46,%47,%48,%49,%50,%51,%52,%53,%54,%55,%56,%57,%58,%59,%60,%61,%62,%63,%64,%65,%66,%67,%68,%69,%70,%71,%72,%73,%74,%75,%76,%77,%78,%79,%80,%81,%82,%83,%84,%85,%86,%87,%88,%89,%90,%91,%92,%93,%94,%95}, %96, %97, p, 1, 1, 0, %99;\n}\n"
               : "+f"(d[0]), "+f"(d[1]), "+f"(d[2]), "+f"(d[3]), "+f"(d[4]), "+f"(d[5]), "+f"(d[6]), "+f"(d[7]), "+f"(d[8]), "+f"(d[9]), "+f"(d[10]), "+f"(d[11]), "+f"(d[12]), "+f"(d[13]), "+f"(d[14]), "+f"(d[15]), "+f"(d[16]), "+f"(d[17]), "+f"(d[18]), "+f"(d[19]), "+f"(d[20]), "+f"(d[21]), "+f"(d[22]), "+f"(d[23]), "+f"(d[24]), "+f"(d[25]), "+f"(d[26]), "+f"(d[27]), "+f"(d[28]), "+f"(d[29]), "+f"(d[30]), "+f"(d[31]), "+f"(d[32]), "+f"(d[33]), "+f"(d[34]), "+f"(d[35]), "+f"(d[36]), "+f"(d[37]), "+f"(d[38]), "+f"(d[39]), "+f"(d[40]), "+f"(d[41]), "+f"(d[42]), "+f"(d[43]), "+f"(d[44]), "+f"(d[45]), "+f"(d[46]), "+f"(d[47]), "+f"(d[48]), "+f"(d[49]), "+f"(d[50]), "+f"(d[51]), "+f"(d[52]), "+f"(d[53]), "+f"(d[54]), "+f"(d[55]), "+f"(d[56]), "+f"(d[57]), "+f"(d[58]), "+f"(d[59]), "+f"(d[60]), "+f"(d[61]), "+f"(d[62]), "+f"(d[63]), "+f"(d[64]), "+f"(d[65]), "+f"(d[66]), "+f"(d[67]), "+f"(d[68]), "+f"(d[69]), "+f"(d[70]), "+f"(d[71]), "+f"(d[72]), "+f"(d[73]), "+f"(d[74]), "+f"(d[75]), "+f"(d[76]), "+f"(d[77]), "+f"(d[78]), "+f"(d[79]), "+f"(d[80]), "+f"(d[81]), "+f"(d[82]), "+f"(d[83]), "+f"(d[84]), "+f"(d[85]), "+f"(d[86]), "+f"(d[87]), "+f"(d[88]), "+f"(d[89]), "+f"(d[90]), "+f"(d[91]), "+f"(d[92]), "+f"(d[93]), "+f"(d[94]), "+f"(d[95])
               : "l"(descA), "l"(descB), "n"(scale_d), "n"(tnsp_b));
}
template <int scale_d> __device__ __forceinline__ void wgmma4_n192(float* d, uint32_t da, uint32_t db) {
#define R_ "{%0,%1,%2,%3,%4,%5,%6,%7,%8,%9,%10,%11,%12,%13,%14,%15,%16,%17,%18,%19,%20,%21,%22,%23,%24,%25,%26,%27,%28,%29,%30,%31,%32,%33,%34,%35,%36,%37,%38,%39,%40,%41,%42,%43,%44,%45,%46,%47,%48,%49,%50,%51,%52,%53,%54,%55,%56,%57,%58,%59,%60,%61,%62,%63,%64,%65,%66,%67,%68,%69,%70,%71,%72,%73,%74,%75,%76,%77,%78,%79,%80,%81,%82,%83,%84,%85,%86,%87,%88,%89,%90,%91,%92,%93,%94,%95}"
  asm volatile("{\n.reg .pred p, q;\n.reg .b64 a, b;\nsetp.ne.b32 p, %98, 0;\nsetp.eq.b32 q, 0, 0;\nmov.b64 a, {%96, 0x40000040};\nmov.b64 b, {%97, 0x40000040};\n"
               "wgmma.mma_async.sync.aligned.m64n192k16.f32.bf16.bf16 " R_ ", a, b, p, 1, 1, 0, 1;\nadd.s64 a, a, 2;\nadd.s64 b, b, 128;\n"
               "wgmma.mma_async.sync.aligned.m64n192k16.f32.bf16.bf16 " R_ ", a, b, q, 1, 1, 0, 1;\nadd.s64 a, a, 2;\nadd.s64 b, b, 128;\n"
               "wgmma.mma_async.sync.aligned.m64n192k16.f32.bf16.bf16 " R_ ", a, b, q, 1, 1, 0, 1;\nadd.s64 a, a, 2;\nadd.s64 b, b, 128;\n"
               "wgmma.mma_async.sync.aligned.m64n192k16.f32.bf16.bf16 " R_ ", a, b, q, 1, 1, 0, 1;\n}\n"
               : "+f"(d[0]), "+f"(d[1]), "+f"(d[2]), "+f"(d[3]), "+f"(d[4]), "+f"(d[5]), "+f"(d[6]), "+f"(d[7]), "+f"(d[8]), "+f"(d[9]), "+f"(d[10]), "+f"(d[11]), "+f"(d[12]), "+f"(d[13]), "+f"(d[14]), "+f"(d[15]), "+f"(d[16]), "+f"(d[17]), "+f"(d[18]), "+f"(d[19]), "+f"(d[20]), "+f"(d[21]), "+f"(d[22]), "+f"(d[23]), "+f"(d[24]), "+f"(d[25]), "+f"(d[26]), "+f"(d[27]), "+f"(d[28]), "+f"(d[29]), "+f"(d[30]), "+f"(d[31]), "+f"(d[32]), "+f"(d[33]), "+f"(d[34]), "+f"(d[35]), "+f"(d[36]), "+f"(d[37]), "+f"(d[38]), "+f"(d[39]), "+f"(d[40]), "+f"(d[41]), "+f"(d[42]), "+f"(d[43]), "+f"(d[44]), "+f"(d[45]), "+f"(d[46]), "+f"(d[47]), "+f"(d[48]), "+f"(d[49]), "+f"(d[50]), "+f"(d[51]), "+f"(d[52]), "+f"(d[53]), "+f"(d[54]), "+f"(d[55]), "+f"(d[56]), "+f"(d[57]), "+f"(d[58]), "+f"(d[59]), "+f"(d[60]), "+f"(d[61]), "+f"(d[62]), "+f"(d[63]), "+f"(d[64]), "+f"(d[65]), "+f"(d[66]), "+f"(d[67]), "+f"(d[68]), "+f"(d[69]), "+f"(d[70]), "+f"(d[71]), "+f"(d[72]), "+f"(d[73]), "+f"(d[74]), "+f"(d[75]), "+f"(d[76]), "+f"(d[77]), "+f"(d[78]), "+f"(d[79]), "+f"(d[80]), "+f"(d[81]), "+f"(d[82]), "+f"(d[83]), "+f"(d[84]), "+f"(d[85]), "+f"(d[86]), "+f"(d[87]), "+f"(d[88]), "+f"(d[89]), "+f"(d[90]), "+f"(d[91]), "+f"(d[92]), "+f"(d[93]), "+f"(d[94]), "+f"(d[95])
               : "r"(da), "r"(db), "n"(scale_d));
#undef R_
}
template <int scale_d> __device__ __forceinline__ void wgmma4_n128(float* d, uint32_t da, uint32_t db) {
#define R_ "{%0,%1,%2,%3,%4,%5,%6,%7,%8,%9,%10,%11,%12,%13,%14,%15,%16,%17,%18,%19,%20,%21,%22,%23,%24,%25,%26,%27,%28,%29,%30,%31,%32,%33,%34,%35,%36,%37,%38,%39,%40,%41,%42,%43,%44,%45,%46,%47,%48,%49,%50,%51,%52,%53,%54,%55,%56,%57,%58,%59,%60,%61,%62,%63}"
  asm volatile("{\n.reg .pred p, q;\n.reg .b64 a, b;\nsetp.ne.b32 p, %66, 0;\nsetp.eq.b32 q, 0, 0;\nmov.b64 a, {%64, 0x40000040};\nmov.b64 b, {%65, 0x40000040};\n"
               "wgmma.mma_async.sync.aligned.m64n128k16.f32.bf16.bf16 " R_ ", a, b, p, 1, 1, 0, 1;\nadd.s64 a, a, 2;\nadd.s64 b, b, 128;\n"
               "wgmma.mma_async.sync.aligned.m64n128k16.f32.bf16.bf16 " R_ ", a, b, q, 1, 1, 0, 1;\nadd.s64 a, a, 2;\nadd.s64 b, b, 128;\n"
               "wgmma.mma_async.sync.aligned.m64n128k16.f32.bf16.bf16 " R_ ", a, b, q, 1, 1, 0, 1;\nadd.s64 a, a, 2;\nadd.s64 b, b, 128;\n"
               "wgmma.mma_async.sync.aligned.m64n128k16.f32.bf16.bf16 " R_ ", a, b, q, 1, 1, 0, 1;\n}\n"
               : "+f"(d[0]), "+f"(d[1]), "+f"(d[2]), "+f"(d[3]), "+f"(d[4]), "+f"(d[5]), "+f"(d[6]), "+f"(d[7]), "+f"(d[8]), "+f"(d[9]), "+f"(d[10]), "+f"(d[11]), "+f"(d[12]), "+f"(d[13]), "+f"(d[14]), "+f"(d[15]), "+f"(d[16]), "+f"(d[17]), "+f"(d[18]), "+f"(d[19]), "+f"(d[20]), "+f"(d[21]), "+f"(d[22]), "+f"(d[23]), "+f"(d[24]), "+f"(d[25]), "+f"(d[26]), "+f"(d[27]), "+f"(d[28]), "+f"(d[29]), "+f"(d[30]), "+f"(d[31]), "+f"(d[32]), "+f"(d[33]), "+f"(d[34]), "+f"(d[35]), "+f"(d[36]), "+f"(d[37]), "+f"(d[38]), "+f"(d[39]), "+f"(d[40]), "+f"(d[41]), "+f"(d[42]), "+f"(d[43]), "+f"(d[44]), "+f"(d[45]), "+f"(d[46]), "+f"(d[47]), "+f"(d[48]), "+f"(d[49]), "+f"(d[50]), "+f"(d[51]), "+f"(d[52]), "+f"(d[53]), "+f"(d[54]), "+f"(d[55]), "+f"(d[56]), "+f"(d[57]), "+f"(d[58]), "+f"(d[59]), "+f"(d[60]), "+f"(d[61]), "+f"(d[62]), "+f"(d[63])
               : "r"(da), "r"(db), "n"(scale_d));
#undef R_
}
template <int scale_d> __device__ __forceinline__ void wgmma_n32(float* d, uint64_t descA, uint64_t descB) {
  asm volatile("{\n.reg .pred p;\nsetp.ne.b32 p, %18, 0;\n"
               "wgmma.mma_async.sync.aligned.m64n32k16.f32.bf16.bf16 {%0,%1,%2,%3,%4,%5,%6,%7,%8,%9,%10,%11,%12,%13,%14,%15}, %16, %17, p, 1, 1, 0, 1;\n}\n"
               : "+f"(d[0]), "+f"(d[1]), "+f"(d[2]), "+f"(d[3]), "+f"(d[4]), "+f"(d[5]), "+f"(d[6]), "+f"(d[7]), "+f"(d[8]), "+f"(d[9]), "+f"(d[10]), "+f"(d[11]), "+f"(d[12]), "+f"(d[13]), "+f"(d[14]), "+f"(d[15])
               : "l"(descA), "l"(descB), "n"(scale_d));
}
template <int scale_d, int tnsp_a> __device__ __forceinline__ void wgmma_n40(float* d, uint64_t descA, uint64_t descB) {
  asm volatile("{\n.reg .pred p;\nsetp.ne.b32 p, %22, 0;\n"
               "wgmma.mma_async.sync.aligned.m64n40k16.f32.bf16.bf16 {%0,%1,%2,%3,%4,%5,%6,%7,%8,%9,%10,%11,%12,%13,%14,%15,%16,%17,%18,%19}, %20, %21, p, 1, 1, %23, 1;\n}\n"
               : "+f"(d[0]), "+f"(d[1]), "+f"(d[2]), "+f"(d[3]), "+f"(d[4]), "+f"(d[5]), "+f"(d[6]), "+f"(d[7]), "+f"(d[8]), "+f"(d[9]), "+f"(d[10]), "+f"(d[11]), "+f"(d[12]), "+f"(d[13]), "+f"(d[14]), "+f"(d[15]), "+f"(d[16]), "+f"(d[17]), "+f"(d[18]), "+f"(d[19])
               : "l"(descA), "l"(descB), "n"(scale_d), "n"(tnsp_a));
}
template <int scale_d> __device__ __forceinline__ void wgmma_n40_rs(float* d, const uint32_t* a, uint64_t descB) {
  asm volatile("{\n.reg .pred p;\nsetp.ne.b32 p, %25, 0;\n"
               "wgmma.mma_async.sync.aligned.m64n40k16.f32.bf16.bf16 {%0,%1,%2,%3,%4,%5,%6,%7,%8,%9,%10,%11,%12,%13,%14,%15,%16,%17,%18,%19}, {%20,%21,%22,%23}, %24, p, 1, 1, 1;\n}\n"
               : "+f"(d[0]), "+f"(d[1]), "+f"(d[2]), "+f"(d[3]), "+f"(d[4]), "+f"(d[5]), "+f"(d[6]), "+f"(d[7]), "+f"(d[8]), "+f"(d[9]), "+f"(d[10]), "+f"(d[11]), "+f"(d[12]), "+f"(d[13]), "+f"(d[14]), "+f"(d[15]), "+f"(d[16]), "+f"(d[17]), "+f"(d[18]), "+f"(d[19])
               : "r"(a[0]), "r"(a[1]), "r"(a[2]), "r"(a[3]), "l"(descB), "n"(scale_d));
}
__device__ __forceinline__ void wgmma_copy(float* d, uint32_t da, uint64_t descB) {
  asm volatile("{\n.reg .pred p;\n.reg .b64 a;\nsetp.ne.b32 p, 0, 0;\nmov.b64 a, {%64, 0x40000040};\n"
               "wgmma.mma_async.sync.aligned.m64n16k16.f32.bf16.bf16 {%0,%1,%2,%3,%4,%5,%6,%7}, a, %65, p, 1, 1, 0, 0;\nadd.s64 a, a, 2;\n"
               "wgmma.mma_async.sync.aligned.m64n16k16.f32.bf16.bf16 {%8,%9,%10,%11,%12,%13,%14,%15}, a, %65, p, 1, 1, 0, 0;\nadd.s64 a, a, 2;\n"
               "wgmma.mma_async.sync.aligned.m64n16k16.f32.bf16.bf16 {%16,%17,%18,%19,%20,%21,%22,%23}, a, %65, p, 1, 1, 0, 0;\nadd.s64 a, a, 2;\n"
               "wgmma.mma_async.sync.aligned.m64n16k16.f32.bf16.bf16 {%24,%25,%26,%27,%28,%29,%30,%31}, a, %65, p, 1, 1, 0, 0;\nadd.s64 a, a, 1018;\n"
               "wgmma.mma_async.sync.aligned.m64n16k16.f32.bf16.bf16 {%32,%33,%34,%35,%36,%37,%38,%39}, a, %65, p, 1, 1, 0, 0;\nadd.s64 a, a, 2;\n"
               "wgmma.mma_async.sync.aligned.m64n16k16.f32.bf16.bf16 {%40,%41,%42,%43,%44,%45,%46,%47}, a, %65, p, 1, 1, 0, 0;\nadd.s64 a, a, 2;\n"
               "wgmma.mma_async.sync.aligned.m64n16k16.f32.bf16.bf16 {%48,%49,%50,%51,%52,%53,%54,%55}, a, %65, p, 1, 1, 0, 0;\nadd.s64 a, a, 2;\n"
               "wgmma.mma_async.sync.aligned.m64n16k16.f32.bf16.bf16 {%56,%57,%58,%59,%60,%61,%62,%63}, a, %65, p, 1, 1, 0, 0;\n"
               "}\n"
               : "+f"(d[0]), "+f"(d[1]), "+f"(d[2]), "+f"(d[3]), "+f"(d[4]), "+f"(d[5]), "+f"(d[6]), "+f"(d[7]), "+f"(d[8]), "+f"(d[9]), "+f"(d[10]), "+f"(d[11]), "+f"(d[12]), "+f"(d[13]), "+f"(d[14]), "+f"(d[15]), "+f"(d[16]), "+f"(d[17]), "+f"(d[18]), "+f"(d[19]), "+f"(d[20]), "+f"(d[21]), "+f"(d[22]), "+f"(d[23]), "+f"(d[24]), "+f"(d[25]), "+f"(d[26]), "+f"(d[27]), "+f"(d[28]), "+f"(d[29]), "+f"(d[30]), "+f"(d[31]), "+f"(d[32]), "+f"(d[33]), "+f"(d[34]), "+f"(d[35]), "+f"(d[36]), "+f"(d[37]), "+f"(d[38]), "+f"(d[39]), "+f"(d[40]), "+f"(d[41]), "+f"(d[42]), "+f"(d[43]), "+f"(d[44]), "+f"(d[45]), "+f"(d[46]), "+f"(d[47]), "+f"(d[48]), "+f"(d[49]), "+f"(d[50]), "+f"(d[51]), "+f"(d[52]), "+f"(d[53]), "+f"(d[54]), "+f"(d[55]), "+f"(d[56]), "+f"(d[57]), "+f"(d[58]), "+f"(d[59]), "+f"(d[60]), "+f"(d[61]), "+f"(d[62]), "+f"(d[63])
               : "r"(da), "l"(descB));
}
template <int scale_d> __device__ __forceinline__ void wgmma_n192_rs(float* d, const uint32_t* a, uint32_t db) {
  asm volatile("{\n.reg .pred p;\n.reg .b64 b;\nsetp.ne.b32 p, %101, 0;\nmov.b64 b, {%100, 0x40000040};\n"
               "wgmma.mma_async.sync.aligned.m64n192k16.f32.bf16.bf16 {%0,%1,%2,%3,%4,%5,%6,%7,%8,%9,%10,%11,%12,%13,%14,%15,%16,%17,%18,%19,%20,%21,%22,%23,%24,%25,%26,%27,%28,%29,%30,%31,%32,%33,%34,%35,%36,%37,%38,%39,%40,%41,%42,%43,%44,%45,%46,%47,%48,%49,%50,%51,%52,%53,%54,%55,%56,%57,%58,%59,%60,%61,%62,%63,%64,%65,%66,%67,%68,%69,%70,%71,%72,%73,%74,%75,%76,%77,%78,%79,%80,%81,%82,%83,%84,%85,%86,%87,%88,%89,%90,%91,%92,%93,%94,%95}, {%96,%97,%98,%99}, b, p, 1, 1, 1;\n}\n"
               : "+f"(d[0]), "+f"(d[1]), "+f"(d[2]), "+f"(d[3]), "+f"(d[4]), "+f"(d[5]), "+f"(d[6]), "+f"(d[7]), "+f"(d[8]), "+f"(d[9]), "+f"(d[10]), "+f"(d[11]), "+f"(d[12]), "+f"(d[13]), "+f"(d[14]), "+f"(d[15]), "+f"(d[16]), "+f"(d[17]), "+f"(d[18]), "+f"(d[19]), "+f"(d[20]), "+f"(d[21]), "+f"(d[22]), "+f"(d[23]), "+f"(d[24]), "+f"(d[25]), "+f"(d[26]), "+f"(d[27]), "+f"(d[28]), "+f"(d[29]), "+f"(d[30]), "+f"(d[31]), "+f"(d[32]), "+f"(d[33]), "+f"(d[34]), "+f"(d[35]), "+f"(d[36]), "+f"(d[37]), "+f"(d[38]), "+f"(d[39]), "+f"(d[40]), "+f"(d[41]), "+f"(d[42]), "+f"(d[43]), "+f"(d[44]), "+f"(d[45]), "+f"(d[46]), "+f"(d[47]), "+f"(d[48]), "+f"(d[49]), "+f"(d[50]), "+f"(d[51]), "+f"(d[52]), "+f"(d[53]), "+f"(d[54]), "+f"(d[55]), "+f"(d[56]), "+f"(d[57]), "+f"(d[58]), "+f"(d[59]), "+f"(d[60]), "+f"(d[61]), "+f"(d[62]), "+f"(d[63]), "+f"(d[64]), "+f"(d[65]), "+f"(d[66]), "+f"(d[67]), "+f"(d[68]), "+f"(d[69]), "+f"(d[70]), "+f"(d[71]), "+f"(d[72]), "+f"(d[73]), "+f"(d[74]), "+f"(d[75]), "+f"(d[76]), "+f"(d[77]), "+f"(d[78]), "+f"(d[79]), "+f"(d[80]), "+f"(d[81]), "+f"(d[82]), "+f"(d[83]), "+f"(d[84]), "+f"(d[85]), "+f"(d[86]), "+f"(d[87]), "+f"(d[88]), "+f"(d[89]), "+f"(d[90]), "+f"(d[91]), "+f"(d[92]), "+f"(d[93]), "+f"(d[94]), "+f"(d[95])
               : "r"(a[0]), "r"(a[1]), "r"(a[2]), "r"(a[3]), "r"(db), "n"(scale_d));
}
__device__ __forceinline__ uint64_t make_desc(uint32_t addr, uint32_t lbo_bytes, uint32_t sbo_bytes) {
  return (uint64_t)((addr & 0x3FFFF) >> 4) | ((uint64_t)(lbo_bytes >> 4) << 16) | ((uint64_t)(sbo_bytes >> 4) << 32) | (1ull << 62);
}

__device__ __forceinline__ void ldsm_x4(uint32_t addr, uint32_t& r0, uint32_t& r1, uint32_t& r2, uint32_t& r3) {
  asm volatile("ldmatrix.sync.aligned.m8n8.x4.shared.b16 {%0,%1,%2,%3}, [%4];" : "=r"(r0), "=r"(r1), "=r"(r2), "=r"(r3) : "r"(addr) : "memory");
}
__device__ __forceinline__ void ldsm_x4_t(uint32_t addr, uint32_t& r0, uint32_t& r1, uint32_t& r2, uint32_t& r3) {
  asm volatile("ldmatrix.sync.aligned.m8n8.x4.trans.shared.b16 {%0,%1,%2,%3}, [%4];" : "=r"(r0), "=r"(r1), "=r"(r2), "=r"(r3) : "r"(addr) : "memory");
}
__device__ __forceinline__ void stsm_x4(uint32_t addr, uint32_t r0, uint32_t r1, uint32_t r2, uint32_t r3) {
  asm volatile("stmatrix.sync.aligned.m8n8.x4.shared.b16 [%0], {%1,%2,%3,%4};" :: "r"(addr), "r"(r0), "r"(r1), "r"(r2), "r"(r3) : "memory");
}
__device__ __forceinline__ void stsm_x4_t(uint32_t addr, uint32_t r0, uint32_t r1, uint32_t r2, uint32_t r3) {
  asm volatile("stmatrix.sync.aligned.m8n8.x4.trans.shared.b16 [%0], {%1,%2,%3,%4};" :: "r"(addr), "r"(r0), "r"(r1), "r"(r2), "r"(r3) : "memory");
}
__device__ __forceinline__ void sts128(uint32_t addr, uint32_t a, uint32_t b, uint32_t c, uint32_t d) {
  asm volatile("st.shared.v4.u32 [%0], {%1,%2,%3,%4};" :: "r"(addr), "r"(a), "r"(b), "r"(c), "r"(d) : "memory");
}
__device__ __forceinline__ float lds32f(uint32_t addr) {
  float v;
  asm volatile("ld.shared.f32 %0, [%1];" : "=f"(v) : "r"(addr) : "memory");
  return v;
}
__device__ __forceinline__ void sts32f(uint32_t addr, float a) {
  asm volatile("st.shared.f32 [%0], %1;" :: "r"(addr), "f"(a) : "memory");
}
__device__ __forceinline__ void mma_bf16(float (&c)[4], uint32_t a0, uint32_t a1, uint32_t a2, uint32_t a3, uint32_t b0, uint32_t b1) {
  asm volatile("mma.sync.aligned.m16n8k16.row.col.f32.bf16.bf16.f32 {%0,%1,%2,%3}, {%4,%5,%6,%7}, {%8,%9}, {%0,%1,%2,%3};"
               : "+f"(c[0]), "+f"(c[1]), "+f"(c[2]), "+f"(c[3]) : "r"(a0), "r"(a1), "r"(a2), "r"(a3), "r"(b0), "r"(b1));
}
__device__ __forceinline__ void mma_bf16_z(float (&c)[4], uint32_t a0, uint32_t a1, uint32_t a2, uint32_t a3, uint32_t b0, uint32_t b1) {
  asm volatile("mma.sync.aligned.m16n8k16.row.col.f32.bf16.bf16.f32 {%0,%1,%2,%3}, {%4,%5,%6,%7}, {%8,%9}, {%10,%10,%10,%10};"
               : "=f"(c[0]), "=f"(c[1]), "=f"(c[2]), "=f"(c[3]) : "r"(a0), "r"(a1), "r"(a2), "r"(a3), "r"(b0), "r"(b1), "f"(0.f));
}
__device__ __forceinline__ uint32_t movm_t(uint32_t v) {
  uint32_t r;
  asm volatile("movmatrix.sync.aligned.m8n8.trans.b16 %0, %1;" : "=r"(r) : "r"(v));
  return r;
}
__device__ __forceinline__ uint32_t pack_bf16(float lo, float hi) {
  uint32_t r;
  asm("cvt.rn.bf16x2.f32 %0, %1, %2;" : "=r"(r) : "f"(hi), "f"(lo));
  return r;
}
__device__ __forceinline__ float bf_lo(uint32_t v) { return __uint_as_float(v << 16); }
__device__ __forceinline__ float bf_hi(uint32_t v) { return __uint_as_float(v & 0xFFFF0000u); }
__device__ __forceinline__ void split3(float x, uint32_t& h, uint32_t& m, uint32_t& l) {
  h = pack_bf16(x, 0.f); x -= bf_lo(h);
  m = pack_bf16(x, 0.f); x -= bf_lo(m);
  l = pack_bf16(x, 0.f);
}
__device__ __forceinline__ float ex2(float x) { float r; asm("ex2.approx.ftz.f32 %0, %1;" : "=f"(r) : "f"(x)); return r; }
__device__ __forceinline__ float rcp_fast(float x) { float r; asm("rcp.approx.ftz.f32 %0, %1;" : "=f"(r) : "f"(x)); return r; }
__device__ __forceinline__ void red_v4(float* p, float a, float b, float c, float d) {
  asm volatile("red.global.add.v4.f32 [%0], {%1, %2, %3, %4};" :: "l"(p), "f"(a), "f"(b), "f"(c), "f"(d) : "memory");
}
__device__ __forceinline__ uint4 ld_ll(const uint4* p) {
  uint4 v;
  asm volatile("{\n.reg .b64 a, b;\nld.relaxed.gpu.global.v2.b64 {a, b}, [%4];\nmov.b64 {%0, %1}, a;\nmov.b64 {%2, %3}, b;\n}\n"
               : "=r"(v.x), "=r"(v.y), "=r"(v.z), "=r"(v.w) : "l"(p) : "memory");
  return v;
}
__device__ __forceinline__ void st_b64(uint2* p, uint32_t a, uint32_t b) {
  asm volatile("{\n.reg .b64 v;\nmov.b64 v, {%1, %2};\nst.relaxed.gpu.global.b64 [%0], v;\n}\n" :: "l"(p), "r"(a), "r"(b) : "memory");
}
__device__ __forceinline__ void st_b128(uint4* p, uint32_t a, uint32_t b, uint32_t c, uint32_t d) {
  asm volatile("{\n.reg .b128 v;\nmov.b128 v, {%1, %2, %3, %4};\nst.relaxed.gpu.global.b128 [%0], v;\n}\n" :: "l"(p), "r"(a), "r"(b), "r"(c), "r"(d) : "memory");
}
__device__ __forceinline__ uint4 ld_b128(const uint4* p) {
  uint4 v;
  asm volatile("{\n.reg .b128 v;\nld.relaxed.gpu.global.b128 v, [%4];\nmov.b128 {%0, %1, %2, %3}, v;\n}\n" : "=r"(v.x), "=r"(v.y), "=r"(v.z), "=r"(v.w) : "l"(p) : "memory");
  return v;
}

constexpr float LOG2E = 1.4426950408889634f;

struct Params {
  const __nv_bfloat16* x0;
  const __nv_bfloat16* wA_qkv;
  const __nv_bfloat16* wA_o;
  const __nv_bfloat16* wB_qkv;
  const __nv_bfloat16* wB_o;
  const unsigned* epoch;
};

#define ACC_DEF(d, n) _Pragma("unroll") for (int i_ = 0; i_ < (n); i_++) asm volatile("" : "=f"(d[i_]))
#define ACC_FENCE(d, n) _Pragma("unroll") for (int i_ = 0; i_ < (n); i_++) asm volatile("" : "+f"(d[i_]) :: "memory")
#define PIN(a, n) _Pragma("unroll") for (int i_ = 0; i_ < (n); i_++) asm volatile("" : "+f"((a)[i_]))
#define PINU(a, n) _Pragma("unroll") for (int i_ = 0; i_ < (n); i_++) asm volatile("" : "+r"((a)[i_]))

#define V_ADDR(p0, sw) uint32_t va_[2] = {(p0) + (srowoff >> 1) + (lhi ^ lsw2 ^ (sw)), (p0) + (srowoff >> 1) + ((32 + lhi) ^ lsw2 ^ (sw))}
#define STAGE_V(acc) { \
    _Pragma("unroll") for (int j_ = 0; j_ < 4; j_++) { \
      const float* a_ = (acc) + j_ * 8; \
      stsm_x4(va_[j_ & 1] + (j_ >> 1) * 8192, \
              pack_bf16(rs0 * a_[0], rs0 * a_[1]), pack_bf16(rs1 * a_[2], rs1 * a_[3]), pack_bf16(rs0 * a_[4], rs0 * a_[5]), pack_bf16(rs1 * a_[6], rs1 * a_[7])); } }
#define FRAG(dst, acc, TR, grp) { \
    _Pragma("unroll") for (int i_ = 15; i_ >= 0; i_--) { \
      const float r_ = (i_ & 8) ? rs1 : rs0; \
      const uint32_t w_ = pack_bf16(r_ * (acc)[4 * (i_ & 7) + (i_ >> 3) * 2], r_ * (acc)[4 * (i_ & 7) + (i_ >> 3) * 2 + 1]); \
      (dst)[8 + i_] = (TR) ? movm_t(w_) : w_; \
      if (i_ == 8 && warp >= 6 && mm < 15) { \
        _Pragma("unroll") for (int j_ = 0; j_ < 2; j_++) \
          st_b128(g_halo + (size_t)(mm * 8 + jj) * 512 + ((grp) * 4 + warp * 2 - 12 + j_) * 32 + lane, ((dst)[16 + j_ * 4] & ~1u) | H_BIT(l), (dst)[17 + j_ * 4], (dst)[18 + j_ * 4], (dst)[19 + j_ * 4]); } } \
    PINU((dst) + 8, 16); }
#define FRAG_PUT(src, slot) if (warp < 6) { _Pragma("unroll") for (int j_ = 0; j_ < 2; j_++) \
      sts128(sbase + OFF_S + (slot) * 8192 + 2048 + warp * 1024 + j_ * 512 + lane * 16, (src)[j_ * 4], (src)[j_ * 4 + 1], (src)[j_ * 4 + 2], (src)[j_ * 4 + 3]); }
#define FRAG_GET(dst, slot) { _Pragma("unroll") for (int j_ = 0; j_ < 2; j_++) \
      asm volatile("ld.shared.v4.u32 {%0, %1, %2, %3}, [%4];" : "=r"((dst)[j_ * 4]), "=r"((dst)[j_ * 4 + 1]), "=r"((dst)[j_ * 4 + 2]), "=r"((dst)[j_ * 4 + 3]) \
                   : "r"(sbase + OFF_S + (slot) * 8192 + warp * 1024 + j_ * 512 + lane * 16) : "memory"); }
#define RW(j) (((j) >> 1) * 4 + ((j) & 1))
template <int POS> __device__ __forceinline__ float exps16_(float* o, const float* p) {
  float s[4];
#pragma unroll
  for (int j = 0; j < 16; j++) { o[j] = ex2(POS ? p[RW(j)] : -p[RW(j)]); if (j < 4) s[j] = o[j]; else s[j & 3] += o[j]; }
  const float r = (s[0] + s[1]) + (s[2] + s[3]);
  return r + __shfl_xor_sync(0xffffffffu, r, 1);
}
template <int POS> __device__ __forceinline__ void exps16_fix(float* o, const float* p, float& sum) {
  if (__builtin_expect(__any_sync(0xffffffffu, !(sum > SUMLO && sum < SUMHI)), 0)) {
    float m = p[0], q[32];
#pragma unroll
    for (int j = 1; j < 16; j++) m = POS ? fmaxf(m, p[RW(j)]) : fminf(m, p[RW(j)]);
    const float x = __shfl_xor_sync(0xffffffffu, m, 1);
    m = POS ? fmaxf(m, x) : fminf(m, x);
#pragma unroll
    for (int j = 0; j < 16; j++) q[RW(j)] = p[RW(j)] - m;
    sum = exps16_<POS>(o, q);
  }
}
__device__ __forceinline__ void store16(const float* e, float sum, uint32_t dst, uint32_t dsw, int c0) {
  const float inv = rcp_fast(sum);
#pragma unroll
  for (int j = 0; j < 2; j++)
    sts128(dst + (((c0 + j) << 4) ^ dsw), pack_bf16(e[j * 8] * inv, e[j * 8 + 1] * inv), pack_bf16(e[j * 8 + 2] * inv, e[j * 8 + 3] * inv),
           pack_bf16(e[j * 8 + 4] * inv, e[j * 8 + 5] * inv), pack_bf16(e[j * 8 + 6] * inv, e[j * 8 + 7] * inv));
}
template <int POS> __device__ __forceinline__ void expp16(uint32_t* o, float* p) {
  {
#pragma unroll
    for (int r = 0; r < 4; r += 2) {
      float m = p[r];
#pragma unroll
      for (int j = 1; j < 8; j++) m = POS ? fmaxf(m, p[r + RW(j)]) : fminf(m, p[r + RW(j)]);
#pragma unroll
      for (int s = 1; s <= 2; s <<= 1) { const float x = __shfl_xor_sync(0xffffffffu, m, s); m = POS ? fmaxf(m, x) : fminf(m, x); }
#pragma unroll
      for (int j = 0; j < 8; j++) p[r + RW(j)] -= m;
    }
  }
#pragma unroll
  for (int j = 0; j < 8; j++) o[j] = pack_bf16(ex2(POS ? p[2 * j] : -p[2 * j]), ex2(POS ? p[2 * j + 1] : -p[2 * j + 1]));
}
__device__ __forceinline__ void scale32(float* o, const float* p, float c0, float c1) {
#pragma unroll
  for (int i = 0; i < 32; i++) asm volatile("mul.f32 %0, %1, %2;" : "=f"(o[i]) : "f"(p[i]), "f"((i & 2) ? c1 : c0));
}
__device__ __forceinline__ bool any_big(const float* p) {
  float m[4];
#pragma unroll
  for (int i = 0; i < 32; i++) m[i >> 3] = (i & 7) ? fmaf(p[i], p[i], m[i >> 3]) : p[i] * p[i];
  return __any_sync(0xffffffffu, !(fmaxf(fmaxf(m[0], m[1]), fmaxf(m[2], m[3])) < BIGLIM));
}
__device__ __forceinline__ void phiq_a(float* p, bool big) {
  if (__builtin_expect(!big, 1)) {
#pragma unroll
    for (int j = 0; j < 16; j++) p[j] = ex2(p[j]);
  }
}
template <int NEXT> __device__ __forceinline__ void phiq_b(uint32_t* o, float* p, bool big) {
  if (__builtin_expect(big, 0)) {
    expp16<0>(o, p); expp16<1>(o + 8, p);
  } else {
    if (NEXT) phiq_a(p + 16, false);
#pragma unroll
    for (int j = 0; j < 4; j++) {
      const float a = p[4 * j], b = p[4 * j + 1], c = p[4 * j + 2], d = p[4 * j + 3];
      const float ab = a * b, cd = c * d, r = rcp_fast(ab * cd), x = r * cd, y = r * ab;
      o[2 * j] = pack_bf16(x * b, x * a); o[2 * j + 1] = pack_bf16(y * d, y * c);
      o[8 + 2 * j] = pack_bf16(a, b); o[9 + 2 * j] = pack_bf16(c, d);
    }
  }
}
#define SCHED_FENCE() asm volatile("pmevent 0;" ::: "memory")

__global__ void __cluster_dims__(2, 1, 1) __launch_bounds__(384, 1)
mega_kernel(const Params prm  , const __grid_constant__ CUtensorMap tm_x0, const __grid_constant__ CUtensorMap tm_xo, const __grid_constant__ CUtensorMap tm_os,
            const __grid_constant__ CUtensorMap tm_o, const __grid_constant__ CUtensorMap tm_wf,
            const __grid_constant__ CUtensorMap tm_wqA, const __grid_constant__ CUtensorMap tm_wqB,
            const __grid_constant__ CUtensorMap tm_woA, const __grid_constant__ CUtensorMap tm_woB,
            const __grid_constant__ CUtensorMap tm_phi) {
  extern __shared__ __align__(1024) uint8_t smem_raw[];
  const uint32_t sbase = smem_u32(smem_raw);
  const uint32_t bar_full = sbase + OFF_BAR;
  const uint32_t bar_done = bar_full + 384;
  const uint32_t bar_stat = bar_full + 768, bar_stat2 = bar_full + 776, bar_epi = bar_full + 784, bar_phi = bar_full + 936  , bar_halo = bar_full + 904  ;
  const uint32_t bar_xr = bar_full + 800, bar_lx = bar_full + 808, bar_stg = bar_full + 832;
  const uint32_t bar_chk = bar_full + 848;

  const int warp = __shfl_sync(0xffffffffu, threadIdx.x >> 5, 0), lane = threadIdx.x & 31;
  const uint32_t bar_kx = sbase + OFF_ID + 384 + warp * 8;
  uint32_t rank;
  asm volatile("mov.u32 %0, %%cluster_ctarank;" : "=r"(rank));
  const int aux = (int)blockIdx.x - NMAIN, tp = (int)(blockIdx.x >> 1) - 4;
  const int gp = tp < 0 ? 0 : (tp < 32 ? tp & 7 : 1 + (tp - 32) % 7), me = tp < 0 ? tp + 8 : (tp < 32 ? tp >> 3 : 4 + (tp - 32) / 7);
  const int jj = me, cc = gp;
  const int cta = aux >= 0 ? -1 : (cc * 8 + jj) * 2 + (int)rank;
  const int mm = cc * 2 + (int)rank;

#define LOAD_EPOCH() const unsigned epoch = ld_relaxed(prm.epoch), ep1 = epoch + 1; (void)epoch
  int budget = 1 << 22;
  unsigned epoch0 = 0;

  if (cta >= 0) {
    if (warp >= 8 && warp < 10 && elect_one()) {
      const int u = warp - 8;
      const uint32_t fb = bar_full + u * 8;
      mbar_init(fb, 1);
      asm volatile("fence.mbarrier_init.release.cluster;" ::: "memory");
      fence_proxy_async_smem();
      mbar_expect_tx(fb, QST + SLOT);
      if (STAG2 && u) __nanosleep(STAG2);
      tma_load_t(sbase + OFF_RA + u * SLOT, &tm_x0, fb, srcb(jj, u) * 128, mm * 128);
#pragma unroll
      for (int i = 0; i < 6; i++) tma_load_2d(sbase + u * QST + i * 4096, &tm_wqA, fb, jj * 128 + (i >> 1) * 1024, srcb(jj, u) * 128 + (i & 1) * 32);
      PROFT(472 + u);
    }
    __syncwarp();
    if (elect_one()) {
#pragma unroll
      for (int i = 0; i < 4; i++) {
        const int u = warp * 4 + i;
        mbar_init(u < 2 ? bar_kx : bar_full + u * 8, ((u >= 4 && u < 11) || (u > 32 && u != 40)) ? 2 : 1); mbar_init(bar_done + u * 8, 16);
      }
      mbar_init(bar_stat + warp * 16, 0x111111181182ull >> (4 * warp) & 15);
      mbar_init(bar_stat + warp * 16 + 8, 0x111111121811ull >> (4 * warp) & 15);
      mbar_init(bar_chk + 112 + (warp & 7) * 8, 1);
      mbar_init(bar_kx, 1);
      asm volatile("fence.mbarrier_init.release.cluster;" ::: "memory");
    }
    __syncwarp();
    {
      const int tx = threadIdx.x;
      const __nv_bfloat16* pf = (tx < 128) ? prm.x0 + (size_t)(mm * 128 + tx) * D_MODEL + srcb(jj, 0) * 128
                                           : prm.wA_qkv + (size_t)(srcb(jj, rank) * 128 + (tx & 63)) * 3072 + ((tx - 128) >> 6) * 1024 + jj * 128;
      if (tx < 320) asm volatile("prefetch.global.L2 [%0];" :: "l"(pf));
      else if (tx == 320) prefetch_tmap(&tm_x0);
      else if (tx == 352) prefetch_tmap(&tm_wqA);
      else if (tx == 383) epoch0 = ld_relaxed(prm.epoch);
    }
    if (PRL == 0 && lane == 0 && warp >= 8) PROFT(440 + warp - 8);
    __syncthreads();
    if (PRL == 0 && threadIdx.x == 256) PROFT(444);
    asm volatile("barrier.cluster.arrive.relaxed.aligned;" ::: "memory");
  }

  if (cta < 0) {
    LOAD_EPOCH();
    const uint32_t buf = sbase + warp * SLOT, bar = sbase + OFF_BAR + warp * 16;
    const uint32_t lsw = (lane & 7) << 4, lhi = (lane >> 4) << 4, lrow = (lane & 15) * 128;
    const bool el = elect_one();
    if (el) {
      mbar_init(bar, 1); mbar_init(bar + 8, 1);
      asm volatile("fence.mbarrier_init.release.cluster;" ::: "memory");
    }
#pragma unroll 1
    for (int rd = 0; rd < (NLAYERS > 1 ? 5 : 2); rd++) {
      if (rd >= 2 && warp >= 8) break;
      const int tk = rd < 2 ? aux * 12 + warp : aux * 8 + warp;
      const int half = tk & 1;
      const int blk = rd < 2 ? (tk >> 1) * 2 + rd : (4 - rd) * 16 + (tk >> 1);
      const CUtensorMap* tm = rd < 2 ? &tm_wqA : (rd == 2 ? &tm_wqB : &tm_wf);
      const int j0 = (blk & 15) >> 1;
#define AUX_LOAD(n) { const uint32_t d_ = buf + ((n) & 1) * 8192, b_ = bar + ((n) & 1) * 8; const int r_ = kslice(j0, 2 * ((AUXORD >> (4 * (n))) & 7) + half) * 64; \
        mbar_expect_tx(b_, 8192); tma_load_2d(d_, tm, b_, blk * 64, r_); tma_load_2d(d_ + 4096, tm, b_, blk * 64, r_ + 32); }
      if (el) {
        if (rd == 3) { wait_flag(&g_flags.wfready[j0].v, ep1 * 16); fence_proxy_async_global(); }
        AUX_LOAD(0); AUX_LOAD(1);
      }
      __syncwarp();
      float cs[8][4];
#pragma unroll
      for (int i = 0; i < 8; i++) cs[i][0] = cs[i][1] = cs[i][2] = cs[i][3] = 0.f;
#pragma unroll 1
      for (int n = 0; n < 8; n++) {
        const uint32_t tb = buf + (n & 1) * 8192 + lrow;
        mbar_wait(bar + (n & 1) * 8, (n >> 1) & 1);
#pragma unroll
        for (int i = 0; i < 16; i++) {
          uint32_t b0, b1, b2, b3;
          ldsm_x4_t(tb + (i >> 2) * 2048 + (((i & 3) * 32 + lhi) ^ lsw), b0, b1, b2, b3);
          mma_bf16(cs[2 * (i & 3)], 0x3F803F80u, 0x3F803F80u, 0x3F803F80u, 0x3F803F80u, b0, b1);
          mma_bf16(cs[2 * (i & 3) + 1], 0x3F803F80u, 0x3F803F80u, 0x3F803F80u, 0x3F803F80u, b2, b3);
        }
        __syncwarp();
        if (el && n < 6) AUX_LOAD(n + 2);
        __syncwarp();
      }
      if (lane < 4) {
#pragma unroll
        for (int i = 0; i < 8; i++) st_b64(&g_colsum[rd >= 2][blk * 32 + i * 4 + lane][half], __float_as_uint(cs[i][0]), (__float_as_uint(cs[i][1]) & ~3u) | (ep1 & 3));
      }
      __syncwarp();
    }
  } else if (warp >= 8) {
    asm volatile("setmaxnreg.dec.sync.aligned.u32 40;");
    if (warp == 8) {
      const bool el = elect_one();
      cluster_wait();
      if (el) {
        if (PRL == 0) PROFT(445);
#pragma unroll 1
        for (int l = 0; l < NLAYERS; l++) {
          const uint32_t par = l & 1;
          const CUtensorMap* tqk = par ? &tm_wf : &tm_wqA;
          const CUtensorMap* tv = par ? &tm_wqB : &tm_wqA;
          const CUtensorMap* two = par ? &tm_woB : &tm_woA;
          if (l == 1) { LOAD_EPOCH(); wait_flag(&g_flags.wfready[jj].v, ep1 * 16); fence_proxy_async_global(); }
#pragma unroll 1
          for (int u = l ? 0 : EARLY; u < 32; u++) {
            if (u >= 4) mbar_wait_sl(bar_done + (u - 4) * 8, par);
            else mbar_wait_sl(bar_done + (43 + u + (u >> 1)) * 8, par ^ 1);
            const uint32_t fb = bar_full + u * 8;
            const int v = (l || u > 7) ? u : u - 4;
            const bool res = u < 11 || (u >= 18 && u < 22);
            mbar_expect_tx(fb, res ? QST : QST + SLOT);
            const int row = kslice(jj, v < 4 ? v & 1 : (u < 18 ? u - 2 : (u < 22 ? u - 6 : u - 20))) * 64 + (int)rank * 32;
            const int ps = v < 4 ? v >> 1 : (u >= 18), col = jj * 128 + ps * 64;
            const int c0 = par ? jj * 128 + (ps ? 0 : 1024) : col;
            const uint32_t dst = sbase + (u & 3) * QST + rank * 4096;
            tma_load_2d_mc(dst, tqk, fb, c0, row);
            tma_load_2d_mc(dst + 8192, tqk, fb, c0 + (par ? 64 : 1024), row);
            tma_load_2d_mc(dst + 16384, tv, fb, col + 2048, row);
            if (u < 8) PROFL3(472 + u);
          }
#pragma unroll 1
          for (int s = 0; s < 16; s++) {
            if (s < 5) { if (s != 2 && s != 4) mbar_wait_sl(bar_done + (28 + s) * 8, par); }
            else if (s != 14) mbar_wait_sl(bar_done + (27 + s - (s == 15)) * 8, par);
            const uint32_t fb = bar_full + (32 + s) * 8;
            mbar_expect_tx(fb, SLOT);
            tma_load_2d_mc(sbase + rank * 8192 + (uint32_t)((WO_BSLOT >> (4 * s)) & 15) * SLOT, two, fb, jj * 128 + (int)rank * 64, wslice(jj, s) * 64);
            const int ts = s + 1;
            if (s >= 5 && ts < 8) {
              mbar_expect_tx(bar_chk - 8 + ts * 8, SLOT);
              tma_load_t(sbase + (uint32_t)((WO_ASLOT(par) >> (4 * ts)) & 15) * SLOT, &tm_o, bar_chk - 8 + ts * 8, wslice(jj, ts) * 64, mm * 128);
            }
          }
        }
      }
      __syncwarp();
    } else if (warp == 9) {
      const bool el = elect_one();
      if (el) {
#pragma unroll
        for (int i = 0; i < 2; i++) {
          mbar_expect_tx(bar_full + 32 + i * 8, SLOT);
          mbar_wait_sl(bar_full + (i ? OWNW1 : OWNW0) * 8, 0);
          tma_load_t(sbase + OFF_S + i * SLOT, &tm_x0, bar_full + 32 + i * 8, jj * 128 + i * 64, mm * 128);
        }
      }
      __syncwarp();
      LOAD_EPOCH();
#pragma unroll 1
      for (int lp = 0; lp < 4 * NLAYERS; lp++) {
        const int l = lp >> 2, ph = lp & 3;
        if (ph == 3) continue;
        const uint32_t par = l & 1;
        const unsigned* pp = reinterpret_cast<const unsigned*>(g_obuf + (ph >> 1) * 64 + (size_t)(mm * 128 + (ph ? 0 : S_LEN) + ((lane & 7) | PROWS) * 16 + (jj & 1) * 8) * D_MODEL +
                                                               (jj >> 1) * 16 + srcb(jj, lane >> 3) * 128);
        const CUtensorMap* tm = lp ? &tm_o : &tm_x0;
        const int row = mm * 128 + ((ph || !l) ? 0 : S_LEN);
        const uint32_t bit = ph ? O_BIT(l) : X_BIT(l - 1);
        const uint32_t slots = ph ? (uint32_t)(WO_ASLOT(par) >> (ph * 32 - 28)) : 0x8769876u;
        const unsigned long long fr = ph == 0 ? XPACE : ph == 1 ? (par ? FRB : 0x35351F1E1Dull) : 0x27262524232232ull;
        uint32_t no = (lp == 0 || (lp & 7) == 1) ? 0 : (ph == 1 ? NOB : (ph ? NO1 : NOX)), v0 = 0, v1 = 0;
        mbar_wait_sl(ph ? bar_done + ((uint32_t)fr & 63) * 8 : (l ? bar_done + 47 * 8 : bar_full), ph ? par : (l ? par ^ 1 : 0));
        if (el && ph) PROFT(324 + l * 16 + ph);
        __syncwarp();
        if (no && (ph == 1 ? SPD1 : (ph ? SPD2 : SPD0))) __nanosleep(ph == 1 ? SPD1 : (ph ? SPD2 : SPD0));
        if (no) { v0 = ld_relaxed(pp); if (ph != 1) __nanosleep(POLLGAP); v1 = ld_relaxed(pp); }
#pragma unroll 1
        for (int i = lp ? 0 : 4; i < (ph == 1 ? 5 : 7); i++, no >>= 8) {
          uint32_t op[4] = {(lp ? bar_chk + (ph >> 1) * 112 : bar_full + 32) + i * 8  , sbase + ((slots >> (4 * i)) & 15) * SLOT,
                            (uint32_t)(srcb(jj, i) * 128 + (ph >> 1) * 64), bar_done + ((uint32_t)(fr >> (8 * i)) & 63) * 8};
          PINU(op, 4);
          if (el) mbar_expect_tx(op[0], SLOT);
#pragma unroll 1
          for (int it = 0; (no & 0xFF) && it < (1 << 18); it++) {
            no &= __ballot_sync(0xffffffffu, (v0 ^ bit) & 1) >> (8 * i);
            if (no) v0 = ld_relaxed(pp);
            if (!(no & 0xFF)) break;
            no &= __ballot_sync(0xffffffffu, (v1 ^ bit) & 1) >> (8 * i);
            if (no) v1 = ld_relaxed(pp);
          }
          if (i >= (ph ? 1 : 4)) mbar_wait_sl(op[3], par);
          if (el) {
            if (i == 0) PROFT(320 + l * 16 + ph);
            PROFL3(448 + ph * 8 + i);
            tma_load_t(op[1], tm, op[0], op[2], row);
          }
          __syncwarp();
        }
        if (ph == 0 && el) {
          if (l) { wait_flag(&g_flags.xready[l][mm].v, ep1 * 8); fence_proxy_async_global(); }
#pragma unroll 1
          for (int u = 11; u < 34; u++) {
            if (u == 18) u = 22;
            mbar_wait_sl(bar_done + (u - 4) * 8, par);
            if (u == 32) mbar_expect_tx(bar_xr, 2 * SLOT);
            tma_load_t(sbase + OFF_RA + (u & 3) * SLOT, tm, u < 32 ? bar_full + u * 8 : bar_xr, kslice(jj, u < 18 ? u - 2 : (u < 32 ? u - 20 : u - 32)) * 64, row);
          }
        }
        __syncwarp();
      }
      if (el && atomicAdd(&g_flags.done.v, 1) == ep1 * NMAIN - 1) asm volatile("st.relaxed.gpu.global.u32 [%0], %1;" :: "l"(&g_flags.epoch.v), "r"(ep1) : "memory");
      __syncwarp();
      cluster_wait();
    } else {
      const int hw = warp - 10;
      if (elect_one()) {
        const uint32_t fb = bar_full + 16 + hw * 8;
        mbar_expect_tx(fb, QST + SLOT);
#pragma unroll
        for (int i = 0; i < 6; i++) tma_load_2d(sbase + (2 + hw) * QST + i * 4096, &tm_wqA, fb, jj * 128 + (i >> 1) * 1024, srcb(jj, 2 + hw) * 128 + (i & 1) * 32);
        tma_load_t(sbase + OFF_RA + (2 + hw) * SLOT, &tm_x0, fb, srcb(jj, 2 + hw) * 128, mm * 128);
        mbar_arrive_local(fb + 32);
        if (PRL == 0) PROFT(446 + hw);
      }
      __syncwarp();
      const unsigned epoch = hw ? __shfl_sync(0xffffffffu, epoch0, 31) : ld_relaxed(prm.epoch), ep1 = epoch + 1;
      const bool el = elect_one();
      cluster_wait();
      if (hw == 0) {
        mbar_wait_sl(bar_full + 8, 0);
        if (lane < 7) prefetch_tmap(lane == 0 ? &tm_os : lane == 1 ? &tm_o : lane == 2 ? &tm_wf : lane == 3 ? &tm_wqB : lane == 4 ? &tm_woA : lane == 5 ? &tm_woB : &tm_phi);
#pragma unroll 1
        for (int i = 0; i < (NLAYERS > 1 ? 5 : 0); i++) {
          if (i == 0) mbar_wait_sl(bar_done + FD0 * 8, 0);
          if (el) {
            if (i == 0) { mbar_expect_tx(bar_phi, 2 * SLOT + 8192); tma_load_2d(sbase + OFF_PHI, &tm_phi, bar_phi, 0, jj * 128); }
            else tma_load_2d(sbase + 12 * SLOT - 4096 + i * 4096, &tm_wqB, bar_phi, jj * 128 + ((i - 1) >> 1) * 64, mm * 64 + (~i & 1) * 32);
          }
          __syncwarp();
          __nanosleep(PFGAP);
        }
      } else {
        if (lane < 24) {
          const uint32_t one = (lane & 8) ? 0u : 0x3F80u << ((lane & 1) * 16), w = (lane >> 1) & 3;
          sts128(sbase + OFF_ID + lane * 16, w == 0 ? one : 0u, w == 1 ? one : 0u, w == 2 ? one : 0u, w == 3 ? one : 0u);
        }
#pragma unroll 1
        for (int b = 0; b < 2; b++) {
          float4* z = reinterpret_cast<float4*>(g_kv[b] + (jj * 4) * KVH + mm * (4 * KVH / 16)) + lane;
#pragma unroll
          for (int i = 0; i < 6; i++) z[i * 32] = make_float4(0.f, 0.f, 0.f, 0.f);
        }
#pragma unroll 1
        for (int i = 0; i < 16; i++) {
          const int b = i >> 2;
          const uint32_t v = (b == 0 ? O_BIT(0) : b == 1 ? X_BIT(0) : H_BIT(0)) + 1;
          uint4* p = b < 2 ? reinterpret_cast<uint4*>(g_obuf + (size_t)(b * S_LEN + mm * 128 + (i & 3) * 32 + (lane >> 3) * 8) * D_MODEL + jj * 128 + (b ? 0 : 64)) + (lane & 7)
                           : g_halo + (size_t)(mm * 8 + jj) * 512 + i * 32 + lane;
          *p = make_uint4(v, v, v, v);
        }
        fence_proxy_async_global();
      }
      __syncwarp();
      uint32_t chkp = 0;
#pragma unroll 1
      for (int lp = 0; lp < 8 * NLAYERS; lp++) {
        const int l = lp >> 3, tk = lp & 7, ph = tk ? 2 - hw : 0;
        const uint32_t par = l & 1;
        int lane; asm volatile("mov.u32 %0, %%laneid;" : "=r"(lane));
        if (tk == 5 || (hw && tk == 0 && l)) {
          const uint32_t bit = ph ? O_BIT(l) : X_BIT(l - 1);
          uint32_t slots = ph ? (uint32_t)(WO_ASLOT(par) >> (ph * 32 - 28)) : 0x8769876u;
          const uint32_t a0 = sbase + (lane & 7) * 126 + lane * 4 + (lane & 1) * 14;
#pragma unroll 1
          for (int c = 0; c < 7; c++, slots >>= 4) {
            const uint32_t cb = bar_chk + 112 - hw * 112 + c * 8;
#pragma unroll 1
            for (int it = 0; it < (1 << 12); it++) {
              mbar_wait_sl(cb, (chkp >> c) & 1);
              chkp ^= 1u << c;
              if (el) PROFL3(384 + ph * 8 + c);
              uint32_t bad;
              asm volatile("{\n.reg .b32 w<16>;\n"
                           "ld.shared.u32 w0, [%1 + 0];\n"
                           "ld.shared.u32 w1, [%1 + 1024];\n"
                           "ld.shared.u32 w2, [%1 + 2048];\n"
                           "ld.shared.u32 w3, [%1 + 3072];\n"
                           "ld.shared.u32 w4, [%1 + 4096];\n"
                           "ld.shared.u32 w5, [%1 + 5120];\n"
                           "ld.shared.u32 w6, [%1 + 6144];\n"
                           "ld.shared.u32 w7, [%1 + 7168];\n"
                           "ld.shared.u32 w8, [%1 + 8192];\n"
                           "ld.shared.u32 w9, [%1 + 9216];\n"
                           "ld.shared.u32 w10, [%1 + 10240];\n"
                           "ld.shared.u32 w11, [%1 + 11264];\n"
                           "ld.shared.u32 w12, [%1 + 12288];\n"
                           "ld.shared.u32 w13, [%1 + 13312];\n"
                           "ld.shared.u32 w14, [%1 + 14336];\n"
                           "ld.shared.u32 w15, [%1 + 15360];\n"
                           "lop3.b32 w0, w0, w1, %2, 0x7E;\n"
                           "lop3.b32 w2, w2, w3, %2, 0x7E;\n"
                           "lop3.b32 w4, w4, w5, %2, 0x7E;\n"
                           "lop3.b32 w6, w6, w7, %2, 0x7E;\n"
                           "lop3.b32 w8, w8, w9, %2, 0x7E;\n"
                           "lop3.b32 w10, w10, w11, %2, 0x7E;\n"
                           "lop3.b32 w12, w12, w13, %2, 0x7E;\n"
                           "lop3.b32 w14, w14, w15, %2, 0x7E;\n"
                           "lop3.b32 w0, w0, w2, w4, 0xFE;\nlop3.b32 w6, w6, w8, w10, 0xFE;\nlop3.b32 w0, w0, w12, w14, 0xFE;\nlop3.b32 %0, w0, w6, 1, 0xA8;\n}\n"
                           : "=r"(bad) : "r"(a0 + (slots & 15) * SLOT), "r"(bit) : "memory");
              if (__all_sync(0xffffffffu, bad == 0)) break;
              if (el) {
                fence_proxy_async_smem();
                mbar_expect_tx(cb, SLOT);
                tma_load_t(sbase + (slots & 15) * SLOT, &tm_o, cb, srcb(jj, c) * 128 + (ph >> 1) * 64, mm * 128 + (ph ? 0 : S_LEN));
                RETRY_COUNT();
              }
              __syncwarp();
            }
            if (el) { mbar_arrive_local(bar_full + (c + (ph ? 25 + ph * 8 : 4)) * 8); PROFL3(416 + ph * 8 + c); }
            __syncwarp();
          }
        } else if (hw && (tk & 5) == 1) {
          {
            const int hp = tk >> 1;
            const uint4* src = reinterpret_cast<const uint4*>(g_colsum[par][jj * 64 + hp * 32 + lane]);
            uint32_t bad;
            int it = 0;
            float c[6];
            do {
              bad = 0;
#pragma unroll
              for (int p = 0; p < 3; p++) {
                const uint4 v = ld_ll(src + ((par && p < 2) ? (hp ? -32 : 512) + p * 32 : p * 512));
                bad |= (v.y ^ ep1) | (v.w ^ ep1);
                c[2 * p] = __uint_as_float(v.x) + __uint_as_float(v.z); c[2 * p + 1] = __uint_as_float(v.y) + __uint_as_float(v.w);
              }
              bad &= 3;
              if (bad) __nanosleep(CSGAP);
            } while (bad && ++it < (1 << 16));
#pragma unroll
            for (int p = 0; p < 6; p++) {
              uint32_t h, m, lo;
              split3(c[p], h, m, lo);
              sts128(sbase + OFF_LNB + hp * 4096 + (p >> 1) * 1024 + lane * 32 + (p & 1) * 16, h | (m << 16), h | (lo << 16), h | (m << 16), lo | (m << 16));
            }
            fence_proxy_async_smem();
            __syncwarp();
            if (el) { mbar_arrive_local(hp ? bar_stat2 : bar_stat); if (hp == 0) PROFT(324 + l * 16); }
            __syncwarp();
          }
        } else if (tk == 0) {
          mbar_wait_sl(bar_done + (l ? 24 : 56), par);
          const uint4* sp = reinterpret_cast<const uint4*>(g_stats + (size_t)(mm * 128) * 8) + lane;
          if (el) PROFL3(484);
#pragma unroll 1
          for (int hf = 2 * hw; hf < (l ? 4 : 2 + 2 * hw); hf++) {
            if (NLAYERS > 1 && l == 0 && el) tma_load_2d(sbase + 11 * SLOT + hf * 4096, &tm_wqB, bar_phi, 1024 + jj * 128 + (hf >> 1) * 64, mm * 64 + (hf & 1) * 32);
            __syncwarp();
            uint4 v[4];
            uint32_t bad;
            int it = 0;
            do {
              bad = 0;
#pragma unroll
              for (int i = 0; i < 4; i++) { v[i] = ld_ll(sp + (hf * 4 + i) * 32); bad |= (v[i].y ^ STAT_TAG(l)) | (v[i].w ^ STAT_TAG(l)); }
              bad &= 3;
              if (bad) __nanosleep(200);
            } while (bad && ++it < (1 << 16));
            __syncwarp();
            if (el) PROFL3(480 + hf);
            float mean = 0.f, m2 = 0.f;
#pragma unroll
            for (int i = 0; i < 4; i++) {
              float a = __uint_as_float(v[i].x) + __uint_as_float(v[i].z);
              a += __shfl_xor_sync(0xffffffffu, a, 1); a += __shfl_xor_sync(0xffffffffu, a, 2);
              a *= 0.125f;
              const float e0 = __uint_as_float(v[i].x) - a, e1 = __uint_as_float(v[i].z) - a;
              float q = fmaf(fmaf(e0, e0, e1 * e1), 128.f, __uint_as_float(v[i].y) + __uint_as_float(v[i].w));
              q += __shfl_xor_sync(0xffffffffu, q, 1); q += __shfl_xor_sync(0xffffffffu, q, 2);
              if ((lane & 3) == i) { mean = a; m2 = q; }
            }
            const uint32_t row = hf * 32 + (lane & 3) * 8 + (lane >> 2);
            uint32_t h, m, lo;
            split3(-0.5f * mean, h, m, lo);
            sts128(sbase + OFF_LNA + row * 16, h | (h << 16), m | (h << 16), lo | (m << 16), m | (lo << 16));
            sts32f(sbase + OFF_ST + row * 4, rsqrtf(m2 * (1.f / 1024.f) + 1e-5f));
          }
          if (hw) continue;
          fence_proxy_async_smem();
          __syncwarp();
          if (el) { mbar_arrive_local(bar_stat); PROFT(323 + l * 16); }
          __syncwarp();
#pragma unroll 1
          for (int i = 0; i < 8 - 4 * l; i++) {
            asm volatile("prefetch.global.L2 [%0];" :: "l"(i < 4 ? (l ? prm.wB_o : prm.wA_o) + (size_t)cta * 8192 + i * 2048 + lane * 64
                                                                 : prm.wB_qkv + (size_t)(cta * 8 + (i - 4) * 2 + (lane >> 4)) * 3072 + 2048 + (lane & 15) * 64));
            __nanosleep(PFGAP);
          }
        } else if (lp == 3) {
#pragma unroll 1
          for (int c = 0; c < (NLAYERS > 1 ? 8 : 0); c++) {
            if (!(c & 3)) { asm volatile("bar.sync %0, 288;" :: "r"(BAR_WF + (c >> 2)) : "memory"); fence_proxy_async_smem(); }
            if (el) {
              tma_store_2d(&tm_wf, sbase + 11 * SLOT + c * 4096, (c < 4 ? 1024 : -128) + jj * 128 + (c >> 1) * 64, mm * 64 + (c & 1) * 32);
              if (c == 7) {
                asm volatile("cp.async.bulk.commit_group;\ncp.async.bulk.wait_group.read 0;" ::: "memory");
                mbar_arrive_local(bar_phi + 8);
              } else __nanosleep(WFGAP);
            }
            __syncwarp();
          }
          if (el) { bulk_commit_wait(); signal_release(&g_flags.wfready[jj].v); PROFT(335); }
          __syncwarp();
        } else if (tk == 2 || tk == 4) {
          if (par) continue;
          const int i = tk >> 2;
          mbar_wait_sl(bar_done + (i ? HW1 : (hw ? 19 : HW0)) * 8, 0);
          const uint4* src = g_halo + (size_t)(mm * 8 + jj - 8) * 512 + i * 256 + hw * 128 + lane;
          uint4 v[4];
          int it = 0;
          bool ok;
          do {
#pragma unroll
            for (int j = 0; j < 4; j++) v[j] = mm ? ld_b128(src + j * 32) : make_uint4(H_BIT(l), 0, 0, 0);
            ok = __all_sync(0xffffffffu, (((v[0].x ^ H_BIT(l)) | (v[1].x ^ H_BIT(l)) | (v[2].x ^ H_BIT(l)) | (v[3].x ^ H_BIT(l))) & 1) == 0);
          } while (!ok && ++it < (1 << 16));
#pragma unroll
          for (int j = 0; j < 4; j++) sts128(sbase + OFF_S + hw * 8192 + j * 512 + lane * 16, v[j].x, v[j].y, v[j].z, v[j].w);
          __syncwarp();
          if (el) { mbar_arrive_local(bar_halo + hw * 8); PROFT(331 + l * 16 + i * 2 + hw); }
          __syncwarp();
        } else if (tk == 6 && hw == 0 && l < NLAYERS - 1) {
          bar_sync<BAR_X1, 288>();
          if (el) {
            PROFT(328 + l * 16);
            mbar_wait_sl(bar_full + XD * 8, par ^ 1);
            tma_store_t(&tm_o, sbase + 11 * SLOT, jj * 128 + 64, mm * 128 + S_LEN);
            bulk_commit_wait();
            signal_release(&g_flags.xready[l + 1][mm].v);
            PROFT(330 + l * 16);
          }
          __syncwarp();
        }
      }
    }
    cluster_sync();
  } else {
    asm volatile("setmaxnreg.inc.sync.aligned.u32 232;");
    const int wg = warp >> 2;
    const int r0 = warp * 16;
    const uint32_t pK = sbase + OFF_S, pV = sbase + OFF_S + SLOT;
#define PMASKS(on, bit) const uint32_t pm0 = ((on) && t == (g >> 1)), pbit = (bit)
#define PBIT(w) (((w) & ~pm0) | (pbit & pm0))
#define LANE_CONSTS() \
    int lane; asm volatile("mov.u32 %0, %%laneid;" : "=r"(lane)); \
    const int g = lane >> 2, t = lane & 3; \
    const uint32_t srowoff = (r0 + (lane & 15)) * 128, lsw = (lane & 7) << 4, lhi = (lane >> 4) << 4, lsw2 = (lane & 6) << 3; \
    (void)g; (void)t; (void)srowoff; (void)lsw; (void)lhi; (void)lsw2;
    uint32_t stgp = 0, peer;
    asm volatile("mapa.shared::cluster.u32 %0, %1, %2;" : "=r"(peer) : "r"(sbase), "r"(rank ^ 1));
    peer -= sbase;
    const uint32_t dA0 = (((sbase & 0x3FFFF) + wg * 8192) >> 4) | 0x10000u, dB0 = ((sbase & 0x3FFFF) >> 4) | 0x2000000u;
#define DESC(lo, hi) ((uint64_t)(uint32_t)(lo) | ((uint64_t)(hi) << 32))
#define STG_ARRIVE() { __syncwarp(); if (elect_one()) mbar_arrive_local(bar_stg); }
#define STG_WAIT() { mbar_wait(bar_stg, stgp); stgp ^= 1; }
#define PROFS() do {} while (0)
#define REL(addr) { if (elect_one()) { mbar_arrive_local(addr); asm volatile("mbarrier.arrive.shared::cluster.b64 _, [%0];" :: "r"((addr) + peer) : "memory"); } }
#define QSTEP(ACC, DA, SC) { \
      const uint32_t da = (DA), db = dB0 + (ub & 0x18) * (QST >> 7); \
      mbar_wait(ub, par); \
      wgmma_fence(); \
      wgmma4_n192<SC>(ACC, da, db); \
      wgmma_commit(); PROFS(); }
#define QREL() { wgmma_wait<1>(); REL(ub + 376); ub += 8; }
#define RA_CUR (dA0 + (OFF_RA >> 4) + (ub & 0x18) * (SLOT >> 7))
#define PUMP1() { QSTEP(S1, RA_CUR, 1); QREL(); }
#define PUMPN() { wgmma_fence(); wgmma4_n192<1>(S1, RA_CUR, dB0 + (ub & 0x18) * (QST >> 7)); wgmma_commit(); PROFS(); QREL(); }
#define PUMP0() { PUMP1(); SCHED_FENCE(); }
#define WSTEP() { \
      const uint32_t s4 = (ub - bar_full - 256) >> 1; \
      const uint32_t da = dA0 + (((uint32_t)(WO_ASLOT(par) >> s4) & 15) << 10), db = dB0 + (((uint32_t)(WO_BSLOT >> s4) & 15) << 10); \
      mbar_wait(ub, par); \
      wgmma_fence(); \
      wgmma4_n128<1>(S1, da, db); \
      wgmma_commit(); PROFS(); \
      wgmma_wait<1>(); \
      if (s4) REL(ub + 376); \
      ub += 8; }
#define PUMPS(n) { _Pragma("unroll 1") for (int i_ = 0; i_ < (n); i_++) PUMP1(); }
#define LNSTEP(ACC, hh) { wgmma_fence(); wgmma_n192<1, 0>(ACC, make_desc(sbase + OFF_LNA + wg * 1024, 0, 128) ^ (1ull << 62), make_desc(sbase + OFF_LNB + (hh) * 4096, 0, 128) ^ (1ull << 62)); }
#define WARP_STORE(tm, tile, col, row) { fence_proxy_async_smem(); __syncwarp(); WARP_STORE0(tm, tile, col, row); }
#define WARP_STORE0(tm, tile, col, row) { \
      if (elect_one()) { tma_store_2d(tm, (tile) + r0 * 128, col, (row) + r0); asm volatile("cp.async.bulk.commit_group;" ::: "memory"); } __syncwarp(); }
#define TILE_CONSTS(base, on, bit) \
      uint32_t ta[5]; \
      { PMASKS(on, bit); (void)pbit; ta[4] = pm0; } \
      _Pragma("unroll") for (int j = 0; j < 4; j++) ta[j] = (base) + srowoff + ((((uint32_t)j << 5) + lhi) ^ lsw); \
      PINU(ta, 5); SCHED_FENCE(); \
      const uint32_t pm0 = ta[4], pbit = (bit)
#define X_OUT(pc, W) { \
      _Pragma("unroll") for (int j = 0; j < 4; j++) \
        stsm_x4(ta[j] + (pc) * SLOT, \
                PBIT(pack_bf16((W)[j * 8 + 0], (W)[j * 8 + 1])), PBIT(pack_bf16((W)[j * 8 + 2], (W)[j * 8 + 3])), \
                (pack_bf16((W)[j * 8 + 4], (W)[j * 8 + 5])), (pack_bf16((W)[j * 8 + 6], (W)[j * 8 + 7]))); }
#define REST_P1(SKEW) { \
      mbar_wait(bar_stat2, par); \
      LNSTEP(S1, 1); \
      wgmma_commit(); \
      _Pragma("unroll 1") while (ub < bar_full + 256) { \
        const bool hold = ub == bar_full + 256 - 8 * (SKEW) && wg == 0; \
        if (hold) { wgmma_wait<0>(); REL(ub + 376); bar_sync<BAR_SKEW, 256>(); } \
        QSTEP(S1, RA_CUR, 1); \
        if (ub == bar_full + 248 && wg == 1) bar_arrive<BAR_SKEW, 256>(); \
        wgmma_wait<1>(); if (!hold) REL(ub + 376); ub += 8; \
      } \
      mbar_wait(bar_done + (31 - (SKEW)) * 8, par);        \
      wgmma_wait<0>(); \
      ACC_FENCE(S1, 96); \
      REL(bar_done + 31 * 8); \
      PROF(13); }
#define FOLD(tile, rd) { \
          LANE_CONSTS(); \
          float d[32]; \
          ACC_DEF(d, 32); \
          mbar_wait(bar_phi, 0); \
          wgmma_fence(); \
          _Pragma("unroll") for (int i = 0; i < 2; i++) { \
            const uint64_t da = make_desc((tile) + wg * 8192 + i * 64, 16, 1024); \
            const uint64_t db = make_desc(sbase + OFF_PHI + wg * 4096 + i * 2048, 16, 512) ^ (3ull << 62); \
            wgmma_n32<0>(d + i * 16, da, db); wgmma_n32<1>(d + i * 16, da + 2, db + 64); \
          } \
          wgmma_commit(); \
          PUMP0(); \
          ACC_FENCE(d, 32); \
          bar_wg(wg); \
          _Pragma("unroll") for (int i = 0; i < 4; i++) { \
            const float* x = d + (i & 1) * 8 + (i >> 1) * 2; \
            if (rd) sts128((tile) + wg * 8192 + ((warp & 3) * 16 + (i >> 1) * 8 + g) * 128 + (((2 * t + (i & 1)) ^ g) << 4), \
                           pack_bf16(x[0], x[1]), pack_bf16(x[4], x[5]), pack_bf16(x[16], x[17]), pack_bf16(x[20], x[21])); \
            else stsm_x4((tile) + srowoff + ((((uint32_t)i << 5) + lhi) ^ lsw), pack_bf16(d[i * 8], d[i * 8 + 1]), pack_bf16(d[i * 8 + 2], d[i * 8 + 3]), \
                         pack_bf16(d[i * 8 + 4], d[i * 8 + 5]), pack_bf16(d[i * 8 + 6], d[i * 8 + 7])); \
          } \
          }
#define XM_ISSUE() { mbar_wait(bar_xr, par); wgmma_fence(); \
      wgmma_copy(T_, dA0 + (OFF_RA >> 4), make_desc(sbase + OFF_ID, 128, 128) ^ (1ull << 62)); }
#define COPYN(d, s, n) _Pragma("unroll") for (int i_ = 0; i_ < (n); i_++) { uint32_t c_; asm volatile("mov.b32 %0, %1;" : "=r"(c_) : "f"((s)[i_])); (d)[i_] = __uint_as_float(c_); }
#define COPY64(d, s) COPYN(d, s, 64)
#define XM_DONE() { ACC_FENCE(T_, 64); COPY64(S1, T_); ACC_FENCE(S1, 64); \
      __syncwarp(); if (elect_one()) mbar_arrive_local(bar_lx); }
#define LOAD_X() { float T_[64]; ACC_DEF(T_, 64); wgmma_wait<0>(); XM_ISSUE(); wgmma_commit(); wgmma_wait<0>(); XM_DONE(); }

    float S0[96], S1[96];
    if (lane == 0) epoch0 = ld_relaxed(prm.epoch);
    __syncwarp();
    uint32_t ub = bar_full;
    {
      constexpr int l = 0;
      constexpr uint32_t par = 0;
      (void)l;
      ACC_DEF(S0, 96);
      QSTEP(S0, RA_CUR, 0);
      PROF(0);
      SCHED_FENCE();
      cluster_wait();
      ub += 8;
#pragma unroll 1
      for (int i = 1; i < 5; i++) {
        QSTEP(S0, dA0 + (OFF_RA >> 4) + i * (SLOT >> 4), 1);
        QREL();
      }
    }
    const unsigned epoch = __shfl_sync(0xffffffffu, epoch0, 0), ep1 = epoch + 1;
#pragma unroll 1
    for (int l = 0;; l++) {
      const uint32_t par = l & 1;
      PROF(1);
      {
        LANE_CONSTS();
        uint32_t ta[4];
#pragma unroll
        for (int j = 0; j < 4; j++) ta[j] = pK + srowoff + ((((uint32_t)j << 5) + lhi) ^ lsw);
        float p0, p1, a0 = 0.f, a1 = 0.f, q0 = 0.f, q1 = 0.f;
#define STATS(j0, j1) _Pragma("unroll") for (int j = (j0); j < (j1); j++) { \
          uint32_t x[4]; \
          ldsm_x4(ta[j & 3] + (j >> 2) * SLOT, x[0], x[1], x[2], x[3]); \
          if (j == 0) { p0 = __shfl_sync(0xffffffffu, bf_lo(x[0]), lane & 28); p1 = __shfl_sync(0xffffffffu, bf_lo(x[1]), lane & 28); } \
          _Pragma("unroll") for (int i = 0; i < 4; i += 2) { \
            const float d0 = bf_lo(x[i]) - p0, d1 = bf_hi(x[i]) - p0, d2 = bf_lo(x[i + 1]) - p1, d3 = bf_hi(x[i + 1]) - p1; \
            a0 += d0 + d1; a1 += d2 + d3; \
            q0 = fmaf(d1, d1, fmaf(d0, d0, q0)); q1 = fmaf(d3, d3, fmaf(d2, d2, q1)); } } \
          asm volatile("" : "+f"(a0), "+f"(a1), "+f"(q0), "+f"(q1), "+f"(p0), "+f"(p1)); SCHED_FENCE()
        if (SB0) { STATS(0, SB0); }
        bar_wg(wg);
        QSTEP(S0, dA0 + ((OFF_S + SLOT) >> 4), 1);
        QREL();
        SCHED_FENCE();
        STATS(SB0, SB1);
        ACC_DEF(S1, 96);
        QSTEP(S1, dA0 + (OFF_S >> 4), 0);
        QREL();
        SCHED_FENCE();
        STATS(SB1, SB2);
        QSTEP(S1, dA0 + ((OFF_S + SLOT) >> 4), 1);
        QREL();
        SCHED_FENCE();
        STATS(SB2, 8);
#pragma unroll
        for (int o = 1; o <= 2; o <<= 1) {
          a0 += __shfl_xor_sync(0xffffffffu, a0, o); a1 += __shfl_xor_sync(0xffffffffu, a1, o);
          q0 += __shfl_xor_sync(0xffffffffu, q0, o); q1 += __shfl_xor_sync(0xffffffffu, q1, o);
        }
        if (t == 1) { a0 = a1; q0 = q1; p0 = p1; }
        if (t < 2) st_b64(g_stats + (size_t)(mm * 128 + r0 + g + t * 8) * 8 + jj, __float_as_uint(fmaf(a0, 1.f / 128.f, p0)),
                          (__float_as_uint(fmaxf(fmaf(a0 * (-1.f / 128.f), a0, q0), 0.f)) & ~3u) | STAT_TAG(l));
        if (l) { asm volatile("cp.async.bulk.wait_group 0;" ::: "memory"); bar_arrive<BAR_X1, 288>(); }
#pragma unroll 1
        while (ub < bar_full + 144) {
          QSTEP(S0, RA_CUR, 1);
          if (ub == bar_full + 64) PROF(2);
          QREL();
        }
      }
      if (XP0 && l == 0) PUMP1();
      LANE_CONSTS();
      mbar_wait(bar_stat, par);
      LNSTEP(S0, 0);
      wgmma_commit();
      const float rs0 = lds32f(sbase + OFF_ST + (r0 + g) * 4), rs1 = lds32f(sbase + OFF_ST + (r0 + g + 8) * 4);
      PUMP0();
      ACC_FENCE(S0, 96);
      PROF(3);
      if (!par) {
        constexpr uint32_t par = 0;
        uint32_t qa[16];
        uint32_t kf[24], vf[24];
#define DRAIN_A(ACC, hp, PMP) { \
          LANE_CONSTS(); \
          FRAG(kf, ACC + 32, 0, (hp) * 2); \
          PMP; \
          FRAG(vf, ACC + 64, 1, (hp) * 2 + 1); \
          _Pragma("unroll") for (int i_ = 0; i_ < 16; i_++) qa[i_] = pack_bf16(ACC[2 * i_], ACC[2 * i_ + 1]); \
          PINU(qa, 16); }
        DRAIN_A(S0, 0, PUMP0());
        if (l == 0 && NLAYERS > 1) {
#pragma unroll 1
          for (int rd = 1; rd >= 0; rd--) {
            FOLD(sbase + (12 - rd) * SLOT, rd);
            asm volatile("bar.arrive %0, 288;" :: "r"(BAR_WF + 1 - rd) : "memory");
          }
        }
        PUMPS(FPUMP - (XP0 && l == 0));
#pragma unroll 1
        for (int h = 0; h < 2; h++) {
          PROFH(4, 16);
          LANE_CONSTS();
          FRAG_PUT(kf + 16, 0); FRAG_PUT(vf + 16, 1);
          STG_ARRIVE();
          if (h) { PROF(8); LOAD_X(); PROF(9); WSTEP(); PROF(10); } else PUMPS(HPUMP2);
          const bool gt0 = 2 * t > g, gt1 = 2 * t >= g;
          uint32_t msk[2] = {(gt0 ? 0xFFFFu : 0u) | (gt1 ? 0xFFFF0000u : 0u), g == 2 * t ? 0x10001u : 0u};
          PINU(msk, 2);
          TILE_CONSTS(sbase, false, 0);
          (void)pm0; (void)pbit;
          if (h) PROF(12);
          STG_WAIT();
          if (h) PROF(14);
          if (warp < 2) mbar_wait(bar_halo, h);
          if (h) PROF(15);
          if (h == 0) mbar_wait(ub, par);
          FRAG_GET(kf, 0);
          PROFH(5, 17);
          float s[2][3][4];
#pragma unroll
          for (int ks = 0; ks < 2; ks++)
#pragma unroll
            for (int i = 0; i < 6; i++) {
              const int hh = i & 1, jb = 2 - (i >> 1);
              const uint32_t* b = kf + jb * 8 + hh * 4 + ks * 2;
              if (ks) mma_bf16(s[hh][jb], qa[hh * 8 + 4], qa[hh * 8 + 5], qa[hh * 8 + 6], qa[hh * 8 + 7], b[0], b[1]);
              else mma_bf16_z(s[hh][jb], qa[hh * 8], qa[hh * 8 + 1], qa[hh * 8 + 2], qa[hh * 8 + 3], b[0], b[1]);
            }
          if (h == 0) PUMPN()
          PROFH(6, 18);
          float va[2][2], vb[2][2], mx[2][2];
#pragma unroll
          for (int hh = 0; hh < 2; hh++) {
            va[hh][0] = gt0 ? s[hh][0][0] : s[hh][1][0];
            vb[hh][0] = gt1 ? s[hh][0][1] : s[hh][1][1];
            va[hh][1] = gt0 ? s[hh][1][2] : s[hh][2][2];
            vb[hh][1] = gt1 ? s[hh][1][3] : s[hh][2][3];
          }
          if (warp < 2 && mm == 0) {
#pragma unroll
            for (int hh = 0; hh < 2; hh++) { if (gt0) va[hh][0] = -INFINITY; if (gt1) vb[hh][0] = -INFINITY; }
          }
#pragma unroll
          for (int i = 0; i < 4; i++) mx[i >> 1][i & 1] = fmaxf(va[i >> 1][i & 1], vb[i >> 1][i & 1]);
#pragma unroll
          for (int o = 1; o <= 2; o <<= 1)
#pragma unroll
            for (int i = 0; i < 4; i++) mx[i >> 1][i & 1] = fmaxf(mx[i >> 1][i & 1], __shfl_xor_sync(0xffffffffu, mx[i >> 1][i & 1], o));
          const float sc0 = rs0 * (0.17677669529663687f * LOG2E), sc1 = rs1 * (0.17677669529663687f * LOG2E);
#pragma unroll
          for (int i = 0; i < 4; i++) {
            const float sc = (i & 1) ? sc1 : sc0, m = mx[i >> 1][i & 1];
            va[i >> 1][i & 1] = ex2((va[i >> 1][i & 1] - m) * sc); vb[i >> 1][i & 1] = ex2((vb[i >> 1][i & 1] - m) * sc);
            mx[i >> 1][i & 1] = va[i >> 1][i & 1] + vb[i >> 1][i & 1];
          }
          if (h == 0) { PIN(&va[0][0], 4); PIN(&vb[0][0], 4); PIN(&mx[0][0], 4); PUMP1(); }
          if (h) PROF(20);
          if (warp < 2) mbar_wait(bar_halo + 8, h);
          if (h) PROF(21);
          if (h == 0) mbar_wait(ub, par);
          FRAG_GET(vf, 1);
#pragma unroll
          for (int o = 1; o <= 2; o <<= 1)
#pragma unroll
            for (int i = 0; i < 4; i++) mx[i >> 1][i & 1] += __shfl_xor_sync(0xffffffffu, mx[i >> 1][i & 1], o);
          float o[8][4];
          uint32_t pa[4][2];
#pragma unroll
          for (int i = 0; i < 4; i++) {
            const float iv = rcp_fast(mx[i >> 1][i & 1]);
            const uint32_t w = pack_bf16(va[i >> 1][i & 1] * iv, vb[i >> 1][i & 1] * iv);
            pa[i][0] = w & msk[0]; pa[i][1] = w & ~msk[0];
          }
          PROFH(7, 19);
#pragma unroll
          for (int i = 7; i >= 0; i--) {
            const uint32_t* a = vf + (i >> 2) * 8 + (i & 3) * 2;
            mma_bf16_z(o[i], a[0], a[1], a[8], a[9], pa[(i & 2) + (i >> 2)][0], pa[(i & 2) + (i >> 2)][1]);
          }
          if (h == 0) PUMPN() else mbar_wait(bar_done + 30 * 8, par);
          if (NLAYERS > 1 && l + h == 0) mbar_wait(bar_phi + 8, 0);
          if (h) PROF(22);
          {
            const uint32_t pm0 = msk[1], pbit = O_BIT(l) * 0x10001u;
#pragma unroll
            for (int i = 0; i < 4; i++)
              stsm_x4_t(ta[i] + (h ? 3 : 12) * SLOT, PBIT(pack_bf16(o[i][0], o[i][1])), PBIT(pack_bf16(o[i + 4][0], o[i + 4][1])),
                        pack_bf16(o[i][2], o[i][3]), pack_bf16(o[i + 4][2], o[i + 4][3]));
          }
          WARP_STORE(&tm_os, sbase + (h ? 3 : 12) * SLOT, jj * 128 + h * 64, mm * 128);
          PROFH(11, 23);
          if (h) break;
          REST_P1(ASKEW);
          asm volatile("cp.async.bulk.wait_group.read 0;" ::: "memory");
          DRAIN_A(S1, 1, {});
        }
      } else {
        constexpr uint32_t par = 1;
        float st[32];
        const float c0 = rs0 * LOG2E, c1 = rs1 * LOG2E;
        { V_ADDR(pV, 0); STAGE_V(S0 + 64); }
        if (warp < 2) sts128(sbase + OFF_ONES + warp * 512 + lane * 16, 0x3F803F80u, 0x3F803F80u, 0x3F803F80u, 0x3F803F80u);
        scale32(st, S0, c0, c1);
        PIN(st, 32);
#define PHI_PIECE(c) { \
          e_[2 * (c)] = ex2(st[2 * (c)]); e_[2 * (c) + 1] = ex2(st[2 * (c) + 1]); \
          _Pragma("unroll") for (int k_ = 4 * (c); k_ < 4 * (c) + 4; k_++) m_[(c) >> 1] = (k_ & 7) ? fmaf(st[k_], st[k_], m_[(c) >> 1]) : st[k_] * st[k_]; \
          asm volatile("" : "+f"(e_[2 * (c)]), "+f"(e_[2 * (c) + 1]), "+f"(m_[(c) >> 1])); SCHED_FENCE(); }
#define PHI_FIN() { \
          big = __any_sync(0xffffffffu, !(fmaxf(fmaxf(m_[0], m_[1]), fmaxf(m_[2], m_[3])) < BIGLIM)); \
          if (__builtin_expect(big, 0)) { COPYN(e_, st, 16); } \
          _Pragma("unroll") for (int k_ = 0; k_ < 16; k_++) st[k_] = e_[k_]; \
          PIN(st, 16); }
#define KV_MMA(vs, IL) { \
          const uint32_t dp = dA0 + 12 * 1024 - wg * 2560, dv = dA0 + (vs) * 1024 + ((OFF_ONES - (vs) * SLOT - 16) << 12) - wg * (512 << 16); \
          STG_WAIT(); \
          fence_proxy_async_smem(); \
          wgmma_fence(); \
          _Pragma("unroll") for (int ks = 0; ks < 8; ks++) { \
            const uint64_t a = DESC(dp + ks * 128, 0x40000040), b = DESC(dv + ks * (64 - (64 << 16)), 0x80000020); \
            if ((IL) && ks) wgmma_fence(); \
            if (ks == 0) wgmma_n40<0, 1>(kv, a, b); else wgmma_n40<1, 1>(kv, a, b); \
            if (ks == 7) wgmma_commit(); \
            if (IL) PHI_PIECE(ks); } }
#define KV_RED1(i) if (h) red_v4(g_kv[l >> 1] + (jj * 4) * KVH + warp * 768 + lane * 4 + (i) * 128, S0[32 + (i) * 3], S0[33 + (i) * 3], S0[34 + (i) * 3], 1.f)
#define KV_REDS(n) { _Pragma("unroll") for (int i_ = 0; i_ < 6; i_++) if (((RPACE >> (4 * i_)) & 15) == (n)) KV_RED1(i_); }
#define KV_SEND(kp) { \
          float sd[9]; \
          _Pragma("unroll") for (int i = 0; i < 8; i++) { (kp)[i] = kv[i]; sd[i] = kv[8 + i]; } \
          (kp)[8] = rank ? kv[18] : kv[16]; sd[8] = rank ? kv[16] : kv[18]; \
          const uint32_t ra = sbase + peer + (warp * 32 + lane) * 4, rb = bar_kx + peer; \
          if (elect_one()) mbar_expect_tx(bar_kx, 1152); \
          _Pragma("unroll") for (int i = 0; i < 2; i++) \
            asm volatile("st.async.weak.shared::cluster.mbarrier::complete_tx::bytes.v4.f32 [%0], {%1, %2, %3, %4}, [%5];" \
                         :: "r"(ra + (warp * 32 + lane) * 12 + OFF_PHI + i * 4096), "f"(sd[4 * i]), "f"(sd[4 * i + 1]), "f"(sd[4 * i + 2]), "f"(sd[4 * i + 3]), "r"(rb) : "memory"); \
          asm volatile("st.async.weak.shared::cluster.mbarrier::complete_tx::bytes.f32 [%0], %1, [%2];" :: "r"(ra + OFF_LNB), "f"(sd[8]), "r"(rb) : "memory"); }
#define KV_RECV(kp, hp) { \
          float r_[9]; \
          float* kvg = g_kv[l >> 1] + (jj * 4 + (hp) * 2) * KVH + warp * 768 + rank * 384 + lane * 4; \
          mbar_wait(bar_kx, l >> 1); \
          _Pragma("unroll") for (int i = 0; i < 2; i++) \
            asm volatile("ld.shared.v4.f32 {%0, %1, %2, %3}, [%4];" : "=f"(r_[4 * i]), "=f"(r_[4 * i + 1]), "=f"(r_[4 * i + 2]), "=f"(r_[4 * i + 3]) \
                         : "r"(sbase + OFF_PHI + i * 4096 + (warp * 32 + lane) * 16) : "memory"); \
          r_[8] = lds32f(sbase + OFF_LNB + (warp * 32 + lane) * 4); \
          _Pragma("unroll") for (int i = 0; i < 3; i++) red_v4(kvg + i * 128, (kp)[3 * i] + r_[3 * i], (kp)[3 * i + 1] + r_[3 * i + 1], (kp)[3 * i + 2] + r_[3 * i + 2], 2.f); }
#define KV_LOAD(hp) { \
          const uint4* kvg = reinterpret_cast<const uint4*>(g_kv[l >> 1] + (jj * 4 + (hp) * 2) * KVH) + warp * 192 + lane; \
          _Pragma("unroll") for (int i = 0; i < 6; i++) v[i] = ld_b128(kvg + i * 32); }
#define KVV(i) __uint_as_float((i) % 3 == 0 ? v[(i) / 3].x : ((i) % 3 == 1 ? v[(i) / 3].y : v[(i) / 3].z))
#define KV_TILE(hp) { \
          _Pragma("unroll 1") for (int it = 0; it < (1 << 16); it++) { \
            if (__all_sync(0xffffffffu, (v[0].w & v[1].w & v[2].w & v[3].w & v[4].w & v[5].w) == 0x41800000u)) break; \
            RETRY_COUNT(); \
            KV_LOAD(hp); \
          } \
          if (hp) PROF(26); else PROF(25); \
          const uint32_t e = lane & 7, jt = ((lane >> 1) & 4) + (e >> 1); \
          const uint32_t row = ((((warp >> 1) ^ wg) & 1) << 5) + ((jt & 1) << 4) + ((warp & 1) << 3) + (jt & 6) + (e & 1); \
          const uint32_t kd = pV + wg * 8192 + row * 128, ksw = (row & 7) << 4; \
          _Pragma("unroll") for (int i = 0; i < 2; i++) \
            stsm_x4(kd + ((i * 32 + lhi) ^ ksw), pack_bf16(KVV(i * 9), KVV(i * 9 + 1)), pack_bf16(KVV(i * 9 + 2), KVV(i * 9 + 3)), \
                    pack_bf16(KVV(i * 9 + 4), KVV(i * 9 + 5)), pack_bf16(KVV(i * 9 + 6), KVV(i * 9 + 7))); \
          stsm_x4(kd + ((64u + lhi) ^ ksw), pack_bf16(KVV(8), 1.f), pack_bf16(KVV(17), 1.f), 0u, 0u); }
#pragma unroll 1
        for (int h = 0; h < 2; h++) {
          PROFH(4, 6);
          PUMP0();
          LANE_CONSTS();
          const uint32_t dsw = (uint32_t)(g ^ (2 * t)) << 4, dst = ((t & 2) ? pK : sbase + 12 * SLOT) + (r0 + g) * 128;
          float e[16], f[16];
          KV_REDS(1);
          float sa = exps16_<0>(e, st);
          exps16_fix<0>(e, st, sa);
          asm volatile("" : "+f"(sa)); PIN(e, 16); PUMP0();
          if (h) STG_WAIT();
          KV_REDS(2);
          store16(e, sa, dst, dsw, 4);
          float sb = exps16_<1>(f, st);
          exps16_fix<1>(f, st, sb);
          asm volatile("" : "+f"(sb)); PIN(f, 16); PUMP0();
          KV_REDS(3);
          store16(f, sb, dst, dsw, 0);
          float sc = exps16_<0>(e, st + 2);
          exps16_fix<0>(e, st + 2, sc);
          asm volatile("" : "+f"(sc)); PIN(e, 16); PUMP0();
          KV_REDS(4);
          store16(e, sc, dst + 1024, dsw, 4);
          float sd = exps16_<1>(f, st + 2);
          exps16_fix<1>(f, st + 2, sd);
          asm volatile("" : "+f"(sd)); PIN(f, 16); PUMP0();
          store16(f, sd, dst + 1024, dsw, 0);
          PROFH(5, 7);
          if (h) break;
          {
            float kv[20];
            ACC_DEF(kv, 20);
            STG_ARRIVE();
            float e_[16], m_[4];
            KV_MMA(11, 0);
            PUMP0();
            ACC_FENCE(kv, 20);
            STG_ARRIVE();
            scale32(st, S0 + 32, c0, c1);
            PIN(st, 32);
            {
              COPYN(S0 + 32, kv, 8); COPYN(S0 + 40, kv + 16, 1); COPYN(S0 + 41, kv + 8, 8); COPYN(S0 + 49, kv + 18, 1);
              const int h = 1;
              KV_REDS(0);
            }
          }
        }
        bool big;
        uint4 v[6];
        {
          float kv[20];
          { LANE_CONSTS(); KV_LOAD(0); }
          mbar_wait(bar_stat2, par);
          ub = bar_full + 240;
          LNSTEP(S1, 1);
          PUMP1();
          if (wg == 0) bar_sync<BAR_SKEW, 256>();
          QSTEP(S1, RA_CUR, 1);
          if (wg == 1) bar_arrive<BAR_SKEW, 256>();
          QREL();
          { LANE_CONSTS(); KV_TILE(0); }
          LANE_CONSTS();
          V_ADDR(sbase + 3 * SLOT, rank * 32);
          PINU(va_, 2);
          mbar_wait(bar_done + 30 * 8, par);
          wgmma_wait<0>();
          ACC_FENCE(S1, 96);
          PROF(13);
          STAGE_V(S1 + 64);
          STG_ARRIVE();
          REL(bar_done + 31 * 8);
          scale32(st, S1, c0, c1);
          PIN(st, 32);
          PROF(16);
          ACC_DEF(kv, 20);
          float e_[16], m_[4];
          KV_MMA(3, 1);
          SCHED_FENCE();
          PROF(14);
          PHI_FIN();
          SCHED_FENCE();
          PROF(15);
          wgmma_wait<0>();
          ACC_FENCE(kv, 20);
          PROF(12);
          { float kp[9]; KV_SEND(kp); _Pragma("unroll") for (int i = 0; i < 3; i++) v[i] = make_uint4(__float_as_uint(kp[3 * i]), __float_as_uint(kp[3 * i + 1]), __float_as_uint(kp[3 * i + 2]), 0u); }
#define VDEF(i0) _Pragma("unroll") for (int i = (i0); i < 6; i++) asm volatile("" : "=r"(v[i].x), "=r"(v[i].y), "=r"(v[i].z), "=r"(v[i].w))
          VDEF(3);
          PROF(17);
        }
#pragma unroll 1
        for (int h = 0; h < 2; h++) {
          const uint32_t pO = sbase + (h ? 3 : 8) * SLOT;
          LANE_CONSTS();
          uint32_t fq[32];
          if (h) { KV_LOAD(1); phiq_a(st, big); PIN(st, 16); PROF(31); }
          PROFH(18, 32);
          SCHED_FENCE();
          phiq_b<1>(fq, st, big); PINU(fq, 16); PIN(st + 16, 16);
          SCHED_FENCE();
          PROFH(8, 9);
          if (h) {
            asm volatile("cp.async.bulk.wait_group.read 0;" ::: "memory");
            mbar_wait(bar_lx, par);
            PROF(30);
            KV_TILE(1);
            STG_ARRIVE();
          }
          SCHED_FENCE();
          if (h == 0) {
            float kp[9];
#pragma unroll
            for (int i = 0; i < 9; i++) kp[i] = KVV(i);
            KV_RECV(kp, 1);
            SCHED_FENCE();
          }
          phiq_b<0>(fq + 16, st + 16, big); PINU(fq + 16, 16);
          PROFH(10, 21);
          if (h) { STG_WAIT(); fence_proxy_async_smem(); }
          wgmma_wait<0>();
          ACC_FENCE(S1, 64);
          PROFH(19, 33);
          float o[4][20];
#define O_MMA(hh) { \
            const uint64_t db = make_desc(pV + (hh) * 8192, 16, 1024); \
            ACC_DEF(o[(hh) * 2], 20); ACC_DEF(o[(hh) * 2 + 1], 20); \
            wgmma_fence(); \
            wgmma_n40_rs<0>(o[(hh) * 2], fq + (hh) * 16, db + 256); wgmma_n40_rs<0>(o[(hh) * 2 + 1], fq + (hh) * 16 + 8, db); \
            wgmma_n40_rs<1>(o[(hh) * 2], fq + (hh) * 16 + 4, db + 384); wgmma_n40_rs<1>(o[(hh) * 2 + 1], fq + (hh) * 16 + 12, db + 128); \
            wgmma_commit(); }
          O_MMA(0);
          SCHED_FENCE();
          PMASKS(true, O_BIT(l));
#pragma unroll
          for (int hh = 0; hh < 2; hh++) {
            wgmma_wait<0>();
            ACC_FENCE(o[hh * 2], 20); ACC_FENCE(o[hh * 2 + 1], 20);
            if (!hh) { O_MMA(1); SCHED_FENCE(); }
            if (hh) PROFH(22, 24);
            const float* x = o[hh * 2];
            const float* y = o[hh * 2 + 1];
            const float sx0 = x[17] * 0x1p-40f, sy0 = y[17] * 0x1p-40f, sx1 = x[19] * 0x1p-40f, sy1 = y[19] * 0x1p-40f;
            const float i0 = rcp_fast(fmaf(fmaf(x[17], 1e-6f, x[16]), sy0, y[16] * sx0)), i1 = rcp_fast(fmaf(fmaf(x[19], 1e-6f, x[18]), sy1, y[18] * sx1));
            const float ax0 = sy0 * i0, ay0 = sx0 * i0, ax1 = sy1 * i1, ay1 = sx1 * i1;
#pragma unroll
            for (int dp = 0; dp < 2; dp++)
              stsm_x4(pO + srowoff + ((hh * 64 + dp * 32 + lhi) ^ lsw),
                      PBIT(pack_bf16(fmaf(x[dp * 8], ax0, y[dp * 8] * ay0), fmaf(x[dp * 8 + 1], ax0, y[dp * 8 + 1] * ay0))),
                      PBIT(pack_bf16(fmaf(x[dp * 8 + 2], ax1, y[dp * 8 + 2] * ay1), fmaf(x[dp * 8 + 3], ax1, y[dp * 8 + 3] * ay1))),
                      (pack_bf16(fmaf(x[dp * 8 + 4], ax0, y[dp * 8 + 4] * ay0), fmaf(x[dp * 8 + 5], ax0, y[dp * 8 + 5] * ay0))),
                      (pack_bf16(fmaf(x[dp * 8 + 6], ax1, y[dp * 8 + 6] * ay1), fmaf(x[dp * 8 + 7], ax1, y[dp * 8 + 7] * ay1))));
          }
          WARP_STORE(&tm_os, pO, jj * 128 + h * 64, mm * 128);
          PROFH(20, 34);
          if (h) break;
          float T_[64];
          scale32(st, S1 + 32, c0, c1);
          PIN(st, 32);
          ACC_DEF(T_, 64);
          XM_ISSUE(); wgmma_commit();
          SCHED_FENCE();
          big = any_big(st);
          SCHED_FENCE();
          PROF(27);
          wgmma_wait<0>(); XM_DONE();
          PROF(28);
          bar_wg(wg);
          WSTEP();
          SCHED_FENCE();
          VDEF(0);
          PROF(29);
        }
      }
      __syncwarp();
      if (elect_one()) mbar_arrive_local(bar_epi);
      bar_wg(wg);
#pragma unroll 1
      while (ub < bar_full + 384) {
        WSTEP();
        if (ub == bar_full + 8 * 41) { asm volatile("cp.async.bulk.wait_group.read 0;" ::: "memory"); PROF(35); }
        if (ub == bar_full + 8 * 42) PROF(36);
      }
      {
        float Wb[32];
        LANE_CONSTS();
        TILE_CONSTS(pK, l < NLAYERS - 1, X_BIT(l));
        if (l < NLAYERS - 1) mbar_wait(bar_full, par ^ 1);
        wgmma_wait<0>();
        ACC_FENCE(S1, 64);
        COPYN(Wb, S1 + 32, 32);
        PROF(37);
        uint32_t xa[16];
#pragma unroll
        for (int i = 0; i < 16; i++) { const uint32_t w = pack_bf16(S1[2 * i], S1[2 * i + 1]); xa[i] = (i & 2) ? w : PBIT(w); }
        PINU(xa, 16);
#define XA_OUT() _Pragma("unroll") for (int j = 0; j < 4; j++) stsm_x4(ta[j], xa[4 * j], xa[4 * j + 1], xa[4 * j + 2], xa[4 * j + 3])
        if (l == NLAYERS - 1) {
          XA_OUT();
          int w; asm volatile("mov.u32 %0, %1;" : "=r"(w) : "r"(warp));
          const int oc = jj * 128 + (w & 1) * 1024, orow = mm * 64 + (w >> 1) * 16 - r0;
          WARP_STORE(&tm_xo, pK, oc, orow);
          { PMASKS(false, 0); X_OUT(1, Wb); }
          WARP_STORE(&tm_xo, pV, oc + 64, orow);
          break;
        }
        PROF(38);
        XA_OUT();
        ACC_DEF(S0, 96);
        wgmma_fence();
        wgmma_n192_rs<0>(S0, xa, dB0);
#pragma unroll
        for (int k = 1; k < RSK; k++) wgmma_n192_rs<1>(S0, xa + 4 * k, dB0 + 128 * k);
        wgmma_commit();
        WARP_STORE(&tm_os, pK, jj * 128, mm * 128 + S_LEN);
        if (RSK < 4) {
          wgmma_fence();
#pragma unroll
          for (int k = RSK; k < 4; k++) wgmma_n192_rs<1>(S0, xa + 4 * k, dB0 + 128 * k);
          wgmma_commit();
        }
        { const int ln_ = l + 1, l = ln_; const uint32_t ub = bar_full; (void)l; (void)ub; PROFS(); }
        REL(bar_done + 47 * 8);
        ub = bar_full + 8;
        PROF(39);
        { PMASKS(false, 0); X_OUT(1, Wb); }
        fence_proxy_async_smem();
      }
    }
    asm volatile("cp.async.bulk.wait_group.read 0;" ::: "memory");
    cluster_sync();
  }
}

typedef CUresult (*PFN_encode)(CUtensorMap*, CUtensorMapDataType, cuuint32_t, void*, const cuuint64_t*, const cuuint64_t*,
                               const cuuint32_t*, const cuuint32_t*, CUtensorMapInterleave, CUtensorMapSwizzle,
                               CUtensorMapL2promotion, CUtensorMapFloatOOBfill);

CUtensorMap make_map(PFN_encode enc, const void* ptr, uint64_t inner, uint64_t outer, uint32_t box_inner, uint32_t box_outer,
                     CUtensorMapSwizzle swz = CU_TENSOR_MAP_SWIZZLE_128B, int promo = CU_TENSOR_MAP_L2_PROMOTION_L2_256B) {
  CUtensorMap m;
  cuuint64_t dims[2] = {inner, outer};
  cuuint64_t strides[1] = {inner * 2};
  cuuint32_t box[2] = {box_inner, box_outer};
  cuuint32_t es[2] = {1, 1};
  enc(&m, CU_TENSOR_MAP_DATA_TYPE_BFLOAT16, 2, const_cast<void*>(ptr), dims, strides, box, es, CU_TENSOR_MAP_INTERLEAVE_NONE,
      swz, (CUtensorMapL2promotion)promo, CU_TENSOR_MAP_FLOAT_OOB_FILL_NONE);
  return m;
}

CUtensorMap make_tile_map(PFN_encode enc, const void* ptr, uint64_t rows, bool by_parity, int promo) {
  CUtensorMap m;
  cuuint64_t dims[4] = {D_MODEL, 16, 2, rows / 32};
  cuuint64_t strides[3] = {by_parity ? 4096u : 2048u, by_parity ? 2048u : 32768u, 65536};
  cuuint32_t box[4] = {64, 16, 2, 4};
  cuuint32_t es[4] = {1, 1, 1, 1};
  enc(&m, CU_TENSOR_MAP_DATA_TYPE_BFLOAT16, 4, const_cast<void*>(ptr), dims, strides, box, es, CU_TENSOR_MAP_INTERLEAVE_NONE,
      CU_TENSOR_MAP_SWIZZLE_128B, (CUtensorMapL2promotion)promo, CU_TENSOR_MAP_FLOAT_OOB_FILL_NONE);
  return m;
}

}

extern "C" void kernel_launch(void* const* d_in, const int* in_sizes, int n_in, void* d_out, int out_size) {
  (void)in_sizes; (void)n_in; (void)out_size;
  static PFN_encode enc = nullptr;
  if (!enc) {
    void* fn = nullptr;
    cudaDriverEntryPointQueryResult qr;
    cudaGetDriverEntryPoint("cuTensorMapEncodeTiled", &fn, cudaEnableDefault, &qr);
    enc = (PFN_encode)fn;
    cudaFuncSetAttribute(mega_kernel, cudaFuncAttributeMaxDynamicSharedMemorySize, SMEM_BYTES);
  }
  Params prm;
  prm.x0 = (const __nv_bfloat16*)d_in[0];
  prm.wA_qkv = (const __nv_bfloat16*)d_in[1];
  prm.wA_o = (const __nv_bfloat16*)d_in[2];
  prm.wB_qkv = (const __nv_bfloat16*)d_in[4];
  prm.wB_o = (const __nv_bfloat16*)d_in[6];
  void *obuf = nullptr, *wf = nullptr, *fl = nullptr;
  cudaGetSymbolAddress(&fl, g_flags);
  prm.epoch = &static_cast<Flags*>(fl)->epoch.v;
  cudaGetSymbolAddress(&obuf, g_obuf);
  cudaGetSymbolAddress(&wf, g_wfold);
  CUtensorMap tm_x0 = make_tile_map(enc, d_in[0], S_LEN, true, XPROMO);
  CUtensorMap tm_xo = make_map(enc, d_out, 2 * D_MODEL, S_LEN / 2, 64, 16);
  CUtensorMap tm_os = make_map(enc, obuf, D_MODEL, 2 * S_LEN, 64, 16);
  CUtensorMap tm_o = make_tile_map(enc, obuf, 2 * S_LEN, false, OPROMO);
  CUtensorMap tm_wf = make_map(enc, wf, 2048, D_MODEL, 64, 32);
  CUtensorMap tm_wqA = make_map(enc, d_in[1], 3 * D_MODEL, D_MODEL, 64, 32, CU_TENSOR_MAP_SWIZZLE_128B, WPROMO);
  CUtensorMap tm_wqB = make_map(enc, prm.wB_qkv, 3 * D_MODEL, D_MODEL, 64, 32);
  CUtensorMap tm_woA = make_map(enc, prm.wA_o, D_MODEL, D_MODEL, 64, 64);
  CUtensorMap tm_woB = make_map(enc, prm.wB_o, D_MODEL, D_MODEL, 64, 64);
  CUtensorMap tm_phi = make_map(enc, d_in[5], 32, 1024, 32, 128, CU_TENSOR_MAP_SWIZZLE_64B);
  mega_kernel<<<NMAIN + NAUX, 384, SMEM_BYTES>>>(prm, tm_x0, tm_xo, tm_os, tm_o, tm_wf, tm_wqA, tm_wqB, tm_woA, tm_woB, tm_phi);
}
```

```cpp
#include <cuda_runtime.h>
#include <cuda.h>
#include <cuda_bf16.h>
#include <stdint.h>

#define NLAYERS 4

#define HPUMP2 1
#define ASKEW 2
#define FPUMP 3
#define PFGAP 100
#define POLLGAP 120
#define HW1 30
#define XPACE 0x06050401000000ull
#define HW0 18
#define XD 4
#define WFGAP 10
#define EARLY 4
#define BIGLIM 3600.f
#define SUMLO 0x1p-100f
#define SUMHI 0x1p100f
#define XPROMO 2
#define OPROMO 3
#define STAG2 0
#define WPROMO 3
#define SB0 2
#define SB1 4
#define SB2 6
#define PROWS 7
#define SPD0 0
#define SPD1 0
#define SPD2 300
#define FRB 0x3535353535ull
#define NOB 0xFFFFFF00u
#define NO1 ~0u
#define NOX ~0u
#define FD0 3
#define CSGAP 300
#define AUXORD 0x76543210
#define OWNW0 1
#define OWNW1 2
#define RPACE 0x221100
#define RSK 2
namespace {

constexpr int S_LEN = 2048, D_MODEL = 1024;
constexpr int NAUX = 4, NMAIN = 128;
constexpr int SLOT = 16384;
constexpr int QST = 24576;
constexpr int OFF_RA = 6 * SLOT, OFF_S = 10 * SLOT;
constexpr int OFF_HALO = 13 * SLOT, OFF_LNB = OFF_HALO  , OFF_ONES = OFF_HALO + 3072;
constexpr int OFF_ST = OFF_HALO + 7168  , OFF_ID = OFF_HALO + 7680, OFF_PHI = OFF_HALO + 8192;
constexpr int OFF_BAR = 14 * SLOT;
constexpr int OFF_LNA = OFF_BAR + 1024;
constexpr int SMEM_BYTES = OFF_LNA + 2048;
#define WO_ASLOT(par) ((par) ? 0x9876CAB39876CA98ull : 0xBC7698A3BC7698BCull)
constexpr unsigned long long WO_BSLOT = 0x5432105421054210ull;
__device__ __forceinline__ int srcb(int j, int i) { return (i + (i >= j)) & 7; }
__device__ __forceinline__ int kslice(int j, int i) { return i < 2 ? 2 * j + i : (i < 9 ? 2 * srcb(j, i - 2) : 2 * srcb(j, i - 9) + 1); }
__device__ __forceinline__ int wslice(int j, int s) { return 2 * ((s & 7) ? srcb(j, (s & 7) - 1) : j) + (s >> 3); }
constexpr int KVH = 6 * 128 * 4;

struct __align__(128) Flag { unsigned v; unsigned pad[31]; };
struct Flags {
  Flag xready[4][16];
  Flag wfready[8];
  Flag done;
  Flag epoch;
};

__device__ Flags g_flags;
__device__ __nv_bfloat16 g_obuf[2 * S_LEN * D_MODEL];
#define O_BIT(l) ((epoch * NLAYERS + (l) + 1) & 1u)
#define X_BIT(l) ((epoch * (NLAYERS - 1) + (l) + 1) & 1u)
__device__ __nv_bfloat16 g_wfold[D_MODEL * 2048];
__device__ uint4 g_halo[16 * 8 * 512];
__device__ __align__(128) float g_kv[2][32 * KVH];
__device__ __align__(128) uint2 g_colsum[2][1536][2];
__device__ __align__(128) uint2 g_stats[S_LEN * 8];
#define H_BIT(l) (NLAYERS > 2 ? (uint32_t)((l) == 0) : (ep1 & 1))
#define STAT_TAG(l) ((ep1 * NLAYERS + (l) + 1) & 3u)

#define RETRY_COUNT()
#define PRL 3
#define PROFL 1
#define PROFW 0
#define PROFT(i) do {} while (0)
#define PROF(i) do {} while (0)
#define PROFH(i, j) do {} while (0)
#define PROFL3(i) do {} while (0)

__device__ __forceinline__ uint32_t smem_u32(const void* p) { return (uint32_t)__cvta_generic_to_shared(p); }
__device__ __forceinline__ bool elect_one() {
  uint32_t p;
  asm volatile("{\n.reg .pred p;\nelect.sync _|p, 0xffffffff;\nselp.u32 %0, 1, 0, p;\n}\n" : "=r"(p));
  return p != 0;
}
__device__ __forceinline__ void mbar_init(uint32_t bar, uint32_t cnt) {
  asm volatile("mbarrier.init.shared::cta.b64 [%0], %1;" :: "r"(bar), "r"(cnt));
}
__device__ __forceinline__ void mbar_expect_tx(uint32_t bar, uint32_t bytes) {
  asm volatile("mbarrier.arrive.expect_tx.shared::cta.b64 _, [%0], %1;" :: "r"(bar), "r"(bytes) : "memory");
}
#define mbar_wait(bar, parity) \
  asm volatile("{\n.reg .pred p, q;\nW_%=:\nmbarrier.try_wait.parity.shared::cta.b64 p, [%1], %2;\nadd.s32 %0, %0, -1;\n" \
               "setp.gt.and.s32 q, %0, 0, !p;\n@q bra.uni W_%=;\n}\n" : "+r"(budget) : "r"((uint32_t)(bar)), "r"((uint32_t)(parity)) : "memory")
#define mbar_wait_sl(bar, parity) \
  asm volatile("{\n.reg .pred p, q;\nW_%=:\nmbarrier.try_wait.parity.shared::cta.b64 p, [%1], %2, 20000;\nadd.s32 %0, %0, -64;\n" \
               "setp.gt.and.s32 q, %0, 0, !p;\n@q bra.uni W_%=;\n}\n" : "+r"(budget) : "r"((uint32_t)(bar)), "r"((uint32_t)(parity)) : "memory")
__device__ __forceinline__ void mbar_arrive_local(uint32_t bar) {
  asm volatile("mbarrier.arrive.shared::cta.b64 _, [%0];" :: "r"(bar) : "memory");
}
__device__ __forceinline__ void tma_load_2d(uint32_t dst, const CUtensorMap* tm, uint32_t bar, int c0, int c1) {
  asm volatile("cp.async.bulk.tensor.2d.shared::cluster.global.mbarrier::complete_tx::bytes [%0], [%1, {%3, %4}], [%2];"
               :: "r"(dst), "l"(tm), "r"(bar), "r"(c0), "r"(c1) : "memory");
}
__device__ __forceinline__ void tma_load_2d_mc(uint32_t dst, const CUtensorMap* tm, uint32_t bar, int c0, int c1) {
  asm volatile("cp.async.bulk.tensor.2d.shared::cluster.global.mbarrier::complete_tx::bytes.multicast::cluster [%0], [%1, {%3, %4}], [%2], %5;"
               :: "r"(dst), "l"(tm), "r"(bar), "r"(c0), "r"(c1), "h"((uint16_t)3) : "memory");
}
__device__ __forceinline__ void tma_store_2d(const CUtensorMap* tm, uint32_t src, int c0, int c1) {
  asm volatile("cp.async.bulk.tensor.2d.global.shared::cta.bulk_group [%0, {%2, %3}], [%1];"
               :: "l"(tm), "r"(src), "r"(c0), "r"(c1) : "memory");
}
__device__ __forceinline__ void tma_load_t(uint32_t dst, const CUtensorMap* tm, uint32_t bar, int c0, int row) {
  asm volatile("cp.async.bulk.tensor.4d.shared::cluster.global.mbarrier::complete_tx::bytes [%0], [%1, {%3, %5, %5, %4}], [%2];"
               :: "r"(dst), "l"(tm), "r"(bar), "r"(c0), "r"(row >> 5), "r"(0) : "memory");
}
__device__ __forceinline__ void tma_store_t(const CUtensorMap* tm, uint32_t src, int c0, int row) {
  asm volatile("cp.async.bulk.tensor.4d.global.shared::cta.bulk_group [%0, {%2, %4, %4, %3}], [%1];"
               :: "l"(tm), "r"(src), "r"(c0), "r"(row >> 5), "r"(0) : "memory");
}
__device__ __forceinline__ void bulk_commit_wait() {
  asm volatile("cp.async.bulk.commit_group;\ncp.async.bulk.wait_group 0;" ::: "memory");
}
__device__ __forceinline__ void prefetch_tmap(const CUtensorMap* tm) {
  asm volatile("prefetch.tensormap [%0];" :: "l"(tm) : "memory");
}
__device__ __forceinline__ void fence_proxy_async_global() { asm volatile("fence.proxy.async.global;" ::: "memory"); }
__device__ __forceinline__ void fence_proxy_async_smem() { asm volatile("fence.proxy.async.shared::cta;" ::: "memory"); }
__device__ __forceinline__ unsigned ld_relaxed(const unsigned* p) {
  unsigned v;
  asm volatile("ld.relaxed.gpu.global.u32 %0, [%1];" : "=r"(v) : "l"(p) : "memory");
  return v;
}
__device__ __forceinline__ void fence_acquire() { asm volatile("fence.acquire.gpu;" ::: "memory"); }
__device__ __forceinline__ void wait_flag(const unsigned* p, unsigned target) {
  int it = 0;
  while ((int)(ld_relaxed(p) - target) < 0 && ++it < (1 << 20)) {}
  fence_acquire();
}
__device__ __forceinline__ void signal_release(unsigned* p) {
  asm volatile("red.release.gpu.global.add.u32 [%0], 1;" :: "l"(p) : "memory");
}
template <int ID, int N> __device__ __forceinline__ void bar_arrive() { asm volatile("bar.arrive %0, %1;" :: "n"(ID), "n"(N) : "memory"); }
template <int ID, int N> __device__ __forceinline__ void bar_sync() { asm volatile("bar.sync %0, %1;" :: "n"(ID), "n"(N) : "memory"); }
__device__ __forceinline__ void bar_wg(int wg) { asm volatile("bar.sync %0, 128;" :: "r"(2 + wg) : "memory"); }
__device__ __forceinline__ void cluster_sync() {
  asm volatile("barrier.cluster.arrive.relaxed.aligned;\nbarrier.cluster.wait.aligned;" ::: "memory");
}
__device__ __forceinline__ void cluster_wait() { asm volatile("barrier.cluster.wait.acquire.aligned;" ::: "memory"); }
enum { BAR_X1 = 7, BAR_WF = 8  , BAR_SKEW = 10 };

__device__ __forceinline__ void wgmma_fence() { asm volatile("wgmma.fence.sync.aligned;" ::: "memory"); }
__device__ __forceinline__ void wgmma_commit() { asm volatile("wgmma.commit_group.sync.aligned;" ::: "memory"); }
template <int N> __device__ __forceinline__ void wgmma_wait() { asm volatile("wgmma.wait_group.sync.aligned %0;" :: "n"(N) : "memory"); }

template <int scale_d, int tnsp_b = 1> __device__ __forceinline__ void wgmma_n192(float* d, uint64_t descA, uint64_t descB) {
  asm volatile("{\n.reg .pred p;\nsetp.ne.b32 p, %98, 0;\n"
               "wgmma.mma_async.sync.aligned.m64n192k16.f32.bf16.bf16 {%0,%1,%2,%3,%4,%5,%6,%7,%8,%9,%10,%11,%12,%13,%14,%15,%16,%17,%18,%19,%20,%21,%22,%23,%24,%25,%26,%27,%28,%29,%30,%31,%32,%33,%34,%35,%36,%37,%38,%39,%40,%41,%42,%43,%44,%45,%46,%47,%48,%49,%50,%51,%52,%53,%54,%55,%56,%57,%58,%59,%60,%61,%62,%63,%64,%65,%66,%67,%68,%69,%70,%71,%72,%73,%74,%75,%76,%77,%78,%79,%80,%81,%82,%83,%84,%85,%86,%87,%88,%89,%90,%91,%92,%93,%94,%95}, %96, %97, p, 1, 1, 0, %99;\n}\n"
               : "+f"(d[0]), "+f"(d[1]), "+f"(d[2]), "+f"(d[3]), "+f"(d[4]), "+f"(d[5]), "+f"(d[6]), "+f"(d[7]), "+f"(d[8]), "+f"(d[9]), "+f"(d[10]), "+f"(d[11]), "+f"(d[12]), "+f"(d[13]), "+f"(d[14]), "+f"(d[15]), "+f"(d[16]), "+f"(d[17]), "+f"(d[18]), "+f"(d[19]), "+f"(d[20]), "+f"(d[21]), "+f"(d[22]), "+f"(d[23]), "+f"(d[24]), "+f"(d[25]), "+f"(d[26]), "+f"(d[27]), "+f"(d[28]), "+f"(d[29]), "+f"(d[30]), "+f"(d[31]), "+f"(d[32]), "+f"(d[33]), "+f"(d[34]), "+f"(d[35]), "+f"(d[36]), "+f"(d[37]), "+f"(d[38]), "+f"(d[39]), "+f"(d[40]), "+f"(d[41]), "+f"(d[42]), "+f"(d[43]), "+f"(d[44]), "+f"(d[45]), "+f"(d[46]), "+f"(d[47]), "+f"(d[48]), "+f"(d[49]), "+f"(d[50]), "+f"(d[51]), "+f"(d[52]), "+f"(d[53]), "+f"(d[54]), "+f"(d[55]), "+f"(d[56]), "+f"(d[57]), "+f"(d[58]), "+f"(d[59]), "+f"(d[60]), "+f"(d[61]), "+f"(d[62]), "+f"(d[63]), "+f"(d[64]), "+f"(d[65]), "+f"(d[66]), "+f"(d[67]), "+f"(d[68]), "+f"(d[69]), "+f"(d[70]), "+f"(d[71]), "+f"(d[72]), "+f"(d[73]), "+f"(d[74]), "+f"(d[75]), "+f"(d[76]), "+f"(d[77]), "+f"(d[78]), "+f"(d[79]), "+f"(d[80]), "+f"(d[81]), "+f"(d[82]), "+f"(d[83]), "+f"(d[84]), "+f"(d[85]), "+f"(d[86]), "+f"(d[87]), "+f"(d[88]), "+f"(d[89]), "+f"(d[90]), "+f"(d[91]), "+f"(d[92]), "+f"(d[93]), "+f"(d[94]), "+f"(d[95])
               : "l"(descA), "l"(descB), "n"(scale_d), "n"(tnsp_b));
}
template <int scale_d> __device__ __forceinline__ void wgmma4_n192(float* d, uint32_t da, uint32_t db) {
#define R_ "{%0,%1,%2,%3,%4,%5,%6,%7,%8,%9,%10,%11,%12,%13,%14,%15,%16,%17,%18,%19,%20,%21,%22,%23,%24,%25,%26,%27,%28,%29,%30,%31,%32,%33,%34,%35,%36,%37,%38,%39,%40,%41,%42,%43,%44,%45,%46,%47,%48,%49,%50,%51,%52,%53,%54,%55,%56,%57,%58,%59,%60,%61,%62,%63,%64,%65,%66,%67,%68,%69,%70,%71,%72,%73,%74,%75,%76,%77,%78,%79,%80,%81,%82,%83,%84,%85,%86,%87,%88,%89,%90,%91,%92,%93,%94,%95}"
  asm volatile("{\n.reg .pred p, q;\n.reg .b64 a, b;\nsetp.ne.b32 p, %98, 0;\nsetp.eq.b32 q, 0, 0;\nmov.b64 a, {%96, 0x40000040};\nmov.b64 b, {%97, 0x40000040};\n"
               "wgmma.mma_async.sync.aligned.m64n192k16.f32.bf16.bf16 " R_ ", a, b, p, 1, 1, 0, 1;\nadd.s64 a, a, 2;\nadd.s64 b, b, 128;\n"
               "wgmma.mma_async.sync.aligned.m64n192k16.f32.bf16.bf16 " R_ ", a, b, q, 1, 1, 0, 1;\nadd.s64 a, a, 2;\nadd.s64 b, b, 128;\n"
               "wgmma.mma_async.sync.aligned.m64n192k16.f32.bf16.bf16 " R_ ", a, b, q, 1, 1, 0, 1;\nadd.s64 a, a, 2;\nadd.s64 b, b, 128;\n"
               "wgmma.mma_async.sync.aligned.m64n192k16.f32.bf16.bf16 " R_ ", a, b, q, 1, 1, 0, 1;\n}\n"
               : "+f"(d[0]), "+f"(d[1]), "+f"(d[2]), "+f"(d[3]), "+f"(d[4]), "+f"(d[5]), "+f"(d[6]), "+f"(d[7]), "+f"(d[8]), "+f"(d[9]), "+f"(d[10]), "+f"(d[11]), "+f"(d[12]), "+f"(d[13]), "+f"(d[14]), "+f"(d[15]), "+f"(d[16]), "+f"(d[17]), "+f"(d[18]), "+f"(d[19]), "+f"(d[20]), "+f"(d[21]), "+f"(d[22]), "+f"(d[23]), "+f"(d[24]), "+f"(d[25]), "+f"(d[26]), "+f"(d[27]), "+f"(d[28]), "+f"(d[29]), "+f"(d[30]), "+f"(d[31]), "+f"(d[32]), "+f"(d[33]), "+f"(d[34]), "+f"(d[35]), "+f"(d[36]), "+f"(d[37]), "+f"(d[38]), "+f"(d[39]), "+f"(d[40]), "+f"(d[41]), "+f"(d[42]), "+f"(d[43]), "+f"(d[44]), "+f"(d[45]), "+f"(d[46]), "+f"(d[47]), "+f"(d[48]), "+f"(d[49]), "+f"(d[50]), "+f"(d[51]), "+f"(d[52]), "+f"(d[53]), "+f"(d[54]), "+f"(d[55]), "+f"(d[56]), "+f"(d[57]), "+f"(d[58]), "+f"(d[59]), "+f"(d[60]), "+f"(d[61]), "+f"(d[62]), "+f"(d[63]), "+f"(d[64]), "+f"(d[65]), "+f"(d[66]), "+f"(d[67]), "+f"(d[68]), "+f"(d[69]), "+f"(d[70]), "+f"(d[71]), "+f"(d[72]), "+f"(d[73]), "+f"(d[74]), "+f"(d[75]), "+f"(d[76]), "+f"(d[77]), "+f"(d[78]), "+f"(d[79]), "+f"(d[80]), "+f"(d[81]), "+f"(d[82]), "+f"(d[83]), "+f"(d[84]), "+f"(d[85]), "+f"(d[86]), "+f"(d[87]), "+f"(d[88]), "+f"(d[89]), "+f"(d[90]), "+f"(d[91]), "+f"(d[92]), "+f"(d[93]), "+f"(d[94]), "+f"(d[95])
               : "r"(da), "r"(db), "n"(scale_d));
#undef R_
}
template <int scale_d> __device__ __forceinline__ void wgmma4_n128(float* d, uint32_t da, uint32_t db) {
#define R_ "{%0,%1,%2,%3,%4,%5,%6,%7,%8,%9,%10,%11,%12,%13,%14,%15,%16,%17,%18,%19,%20,%21,%22,%23,%24,%25,%26,%27,%28,%29,%30,%31,%32,%33,%34,%35,%36,%37,%38,%39,%40,%41,%42,%43,%44,%45,%46,%47,%48,%49,%50,%51,%52,%53,%54,%55,%56,%57,%58,%59,%60,%61,%62,%63}"
  asm volatile("{\n.reg .pred p, q;\n.reg .b64 a, b;\nsetp.ne.b32 p, %66, 0;\nsetp.eq.b32 q, 0, 0;\nmov.b64 a, {%64, 0x40000040};\nmov.b64 b, {%65, 0x40000040};\n"
               "wgmma.mma_async.sync.aligned.m64n128k16.f32.bf16.bf16 " R_ ", a, b, p, 1, 1, 0, 1;\nadd.s64 a, a, 2;\nadd.s64 b, b, 128;\n"
               "wgmma.mma_async.sync.aligned.m64n128k16.f32.bf16.bf16 " R_ ", a, b, q, 1, 1, 0, 1;\nadd.s64 a, a, 2;\nadd.s64 b, b, 128;\n"
               "wgmma.mma_async.sync.aligned.m64n128k16.f32.bf16.bf16 " R_ ", a, b, q, 1, 1, 0, 1;\nadd.s64 a, a, 2;\nadd.s64 b, b, 128;\n"
               "wgmma.mma_async.sync.aligned.m64n128k16.f32.bf16.bf16 " R_ ", a, b, q, 1, 1, 0, 1;\n}\n"
               : "+f"(d[0]), "+f"(d[1]), "+f"(d[2]), "+f"(d[3]), "+f"(d[4]), "+f"(d[5]), "+f"(d[6]), "+f"(d[7]), "+f"(d[8]), "+f"(d[9]), "+f"(d[10]), "+f"(d[11]), "+f"(d[12]), "+f"(d[13]), "+f"(d[14]), "+f"(d[15]), "+f"(d[16]), "+f"(d[17]), "+f"(d[18]), "+f"(d[19]), "+f"(d[20]), "+f"(d[21]), "+f"(d[22]), "+f"(d[23]), "+f"(d[24]), "+f"(d[25]), "+f"(d[26]), "+f"(d[27]), "+f"(d[28]), "+f"(d[29]), "+f"(d[30]), "+f"(d[31]), "+f"(d[32]), "+f"(d[33]), "+f"(d[34]), "+f"(d[35]), "+f"(d[36]), "+f"(d[37]), "+f"(d[38]), "+f"(d[39]), "+f"(d[40]), "+f"(d[41]), "+f"(d[42]), "+f"(d[43]), "+f"(d[44]), "+f"(d[45]), "+f"(d[46]), "+f"(d[47]), "+f"(d[48]), "+f"(d[49]), "+f"(d[50]), "+f"(d[51]), "+f"(d[52]), "+f"(d[53]), "+f"(d[54]), "+f"(d[55]), "+f"(d[56]), "+f"(d[57]), "+f"(d[58]), "+f"(d[59]), "+f"(d[60]), "+f"(d[61]), "+f"(d[62]), "+f"(d[63])
               : "r"(da), "r"(db), "n"(scale_d));
#undef R_
}
template <int scale_d> __device__ __forceinline__ void wgmma_n32(float* d, uint64_t descA, uint64_t descB) {
  asm volatile("{\n.reg .pred p;\nsetp.ne.b32 p, %18, 0;\n"
               "wgmma.mma_async.sync.aligned.m64n32k16.f32.bf16.bf16 {%0,%1,%2,%3,%4,%5,%6,%7,%8,%9,%10,%11,%12,%13,%14,%15}, %16, %17, p, 1, 1, 0, 1;\n}\n"
               : "+f"(d[0]), "+f"(d[1]), "+f"(d[2]), "+f"(d[3]), "+f"(d[4]), "+f"(d[5]), "+f"(d[6]), "+f"(d[7]), "+f"(d[8]), "+f"(d[9]), "+f"(d[10]), "+f"(d[11]), "+f"(d[12]), "+f"(d[13]), "+f"(d[14]), "+f"(d[15])
               : "l"(descA), "l"(descB), "n"(scale_d));
}
template <int scale_d, int tnsp_a> __device__ __forceinline__ void wgmma_n40(float* d, uint64_t descA, uint64_t descB) {
  asm volatile("{\n.reg .pred p;\nsetp.ne.b32 p, %22, 0;\n"
               "wgmma.mma_async.sync.aligned.m64n40k16.f32.bf16.bf16 {%0,%1,%2,%3,%4,%5,%6,%7,%8,%9,%10,%11,%12,%13,%14,%15,%16,%17,%18,%19}, %20, %21, p, 1, 1, %23, 1;\n}\n"
               : "+f"(d[0]), "+f"(d[1]), "+f"(d[2]), "+f"(d[3]), "+f"(d[4]), "+f"(d[5]), "+f"(d[6]), "+f"(d[7]), "+f"(d[8]), "+f"(d[9]), "+f"(d[10]), "+f"(d[11]), "+f"(d[12]), "+f"(d[13]), "+f"(d[14]), "+f"(d[15]), "+f"(d[16]), "+f"(d[17]), "+f"(d[18]), "+f"(d[19])
               : "l"(descA), "l"(descB), "n"(scale_d), "n"(tnsp_a));
}
template <int scale_d> __device__ __forceinline__ void wgmma_n40_rs(float* d, const uint32_t* a, uint64_t descB) {
  asm volatile("{\n.reg .pred p;\nsetp.ne.b32 p, %25, 0;\n"
               "wgmma.mma_async.sync.aligned.m64n40k16.f32.bf16.bf16 {%0,%1,%2,%3,%4,%5,%6,%7,%8,%9,%10,%11,%12,%13,%14,%15,%16,%17,%18,%19}, {%20,%21,%22,%23}, %24, p, 1, 1, 1;\n}\n"
               : "+f"(d[0]), "+f"(d[1]), "+f"(d[2]), "+f"(d[3]), "+f"(d[4]), "+f"(d[5]), "+f"(d[6]), "+f"(d[7]), "+f"(d[8]), "+f"(d[9]), "+f"(d[10]), "+f"(d[11]), "+f"(d[12]), "+f"(d[13]), "+f"(d[14]), "+f"(d[15]), "+f"(d[16]), "+f"(d[17]), "+f"(d[18]), "+f"(d[19])
               : "r"(a[0]), "r"(a[1]), "r"(a[2]), "r"(a[3]), "l"(descB), "n"(scale_d));
}
__device__ __forceinline__ void wgmma_copy(float* d, uint32_t da, uint64_t descB) {
  asm volatile("{\n.reg .pred p;\n.reg .b64 a;\nsetp.ne.b32 p, 0, 0;\nmov.b64 a, {%64, 0x40000040};\n"
               "wgmma.mma_async.sync.aligned.m64n16k16.f32.bf16.bf16 {%0,%1,%2,%3,%4,%5,%6,%7}, a, %65, p, 1, 1, 0, 0;\nadd.s64 a, a, 2;\n"
               "wgmma.mma_async.sync.aligned.m64n16k16.f32.bf16.bf16 {%8,%9,%10,%11,%12,%13,%14,%15}, a, %65, p, 1, 1, 0, 0;\nadd.s64 a, a, 2;\n"
               "wgmma.mma_async.sync.aligned.m64n16k16.f32.bf16.bf16 {%16,%17,%18,%19,%20,%21,%22,%23}, a, %65, p, 1, 1, 0, 0;\nadd.s64 a, a, 2;\n"
               "wgmma.mma_async.sync.aligned.m64n16k16.f32.bf16.bf16 {%24,%25,%26,%27,%28,%29,%30,%31}, a, %65, p, 1, 1, 0, 0;\nadd.s64 a, a, 1018;\n"
               "wgmma.mma_async.sync.aligned.m64n16k16.f32.bf16.bf16 {%32,%33,%34,%35,%36,%37,%38,%39}, a, %65, p, 1, 1, 0, 0;\nadd.s64 a, a, 2;\n"
               "wgmma.mma_async.sync.aligned.m64n16k16.f32.bf16.bf16 {%40,%41,%42,%43,%44,%45,%46,%47}, a, %65, p, 1, 1, 0, 0;\nadd.s64 a, a, 2;\n"
               "wgmma.mma_async.sync.aligned.m64n16k16.f32.bf16.bf16 {%48,%49,%50,%51,%52,%53,%54,%55}, a, %65, p, 1, 1, 0, 0;\nadd.s64 a, a, 2;\n"
               "wgmma.mma_async.sync.aligned.m64n16k16.f32.bf16.bf16 {%56,%57,%58,%59,%60,%61,%62,%63}, a, %65, p, 1, 1, 0, 0;\n"
               "}\n"
               : "+f"(d[0]), "+f"(d[1]), "+f"(d[2]), "+f"(d[3]), "+f"(d[4]), "+f"(d[5]), "+f"(d[6]), "+f"(d[7]), "+f"(d[8]), "+f"(d[9]), "+f"(d[10]), "+f"(d[11]), "+f"(d[12]), "+f"(d[13]), "+f"(d[14]), "+f"(d[15]), "+f"(d[16]), "+f"(d[17]), "+f"(d[18]), "+f"(d[19]), "+f"(d[20]), "+f"(d[21]), "+f"(d[22]), "+f"(d[23]), "+f"(d[24]), "+f"(d[25]), "+f"(d[26]), "+f"(d[27]), "+f"(d[28]), "+f"(d[29]), "+f"(d[30]), "+f"(d[31]), "+f"(d[32]), "+f"(d[33]), "+f"(d[34]), "+f"(d[35]), "+f"(d[36]), "+f"(d[37]), "+f"(d[38]), "+f"(d[39]), "+f"(d[40]), "+f"(d[41]), "+f"(d[42]), "+f"(d[43]), "+f"(d[44]), "+f"(d[45]), "+f"(d[46]), "+f"(d[47]), "+f"(d[48]), "+f"(d[49]), "+f"(d[50]), "+f"(d[51]), "+f"(d[52]), "+f"(d[53]), "+f"(d[54]), "+f"(d[55]), "+f"(d[56]), "+f"(d[57]), "+f"(d[58]), "+f"(d[59]), "+f"(d[60]), "+f"(d[61]), "+f"(d[62]), "+f"(d[63])
               : "r"(da), "l"(descB));
}
template <int scale_d> __device__ __forceinline__ void wgmma_n192_rs(float* d, const uint32_t* a, uint32_t db) {
  asm volatile("{\n.reg .pred p;\n.reg .b64 b;\nsetp.ne.b32 p, %101, 0;\nmov.b64 b, {%100, 0x40000040};\n"
               "wgmma.mma_async.sync.aligned.m64n192k16.f32.bf16.bf16 {%0,%1,%2,%3,%4,%5,%6,%7,%8,%9,%10,%11,%12,%13,%14,%15,%16,%17,%18,%19,%20,%21,%22,%23,%24,%25,%26,%27,%28,%29,%30,%31,%32,%33,%34,%35,%36,%37,%38,%39,%40,%41,%42,%43,%44,%45,%46,%47,%48,%49,%50,%51,%52,%53,%54,%55,%56,%57,%58,%59,%60,%61,%62,%63,%64,%65,%66,%67,%68,%69,%70,%71,%72,%73,%74,%75,%76,%77,%78,%79,%80,%81,%82,%83,%84,%85,%86,%87,%88,%89,%90,%91,%92,%93,%94,%95}, {%96,%97,%98,%99}, b, p, 1, 1, 1;\n}\n"
               : "+f"(d[0]), "+f"(d[1]), "+f"(d[2]), "+f"(d[3]), "+f"(d[4]), "+f"(d[5]), "+f"(d[6]), "+f"(d[7]), "+f"(d[8]), "+f"(d[9]), "+f"(d[10]), "+f"(d[11]), "+f"(d[12]), "+f"(d[13]), "+f"(d[14]), "+f"(d[15]), "+f"(d[16]), "+f"(d[17]), "+f"(d[18]), "+f"(d[19]), "+f"(d[20]), "+f"(d[21]), "+f"(d[22]), "+f"(d[23]), "+f"(d[24]), "+f"(d[25]), "+f"(d[26]), "+f"(d[27]), "+f"(d[28]), "+f"(d[29]), "+f"(d[30]), "+f"(d[31]), "+f"(d[32]), "+f"(d[33]), "+f"(d[34]), "+f"(d[35]), "+f"(d[36]), "+f"(d[37]), "+f"(d[38]), "+f"(d[39]), "+f"(d[40]), "+f"(d[41]), "+f"(d[42]), "+f"(d[43]), "+f"(d[44]), "+f"(d[45]), "+f"(d[46]), "+f"(d[47]), "+f"(d[48]), "+f"(d[49]), "+f"(d[50]), "+f"(d[51]), "+f"(d[52]), "+f"(d[53]), "+f"(d[54]), "+f"(d[55]), "+f"(d[56]), "+f"(d[57]), "+f"(d[58]), "+f"(d[59]), "+f"(d[60]), "+f"(d[61]), "+f"(d[62]), "+f"(d[63]), "+f"(d[64]), "+f"(d[65]), "+f"(d[66]), "+f"(d[67]), "+f"(d[68]), "+f"(d[69]), "+f"(d[70]), "+f"(d[71]), "+f"(d[72]), "+f"(d[73]), "+f"(d[74]), "+f"(d[75]), "+f"(d[76]), "+f"(d[77]), "+f"(d[78]), "+f"(d[79]), "+f"(d[80]), "+f"(d[81]), "+f"(d[82]), "+f"(d[83]), "+f"(d[84]), "+f"(d[85]), "+f"(d[86]), "+f"(d[87]), "+f"(d[88]), "+f"(d[89]), "+f"(d[90]), "+f"(d[91]), "+f"(d[92]), "+f"(d[93]), "+f"(d[94]), "+f"(d[95])
               : "r"(a[0]), "r"(a[1]), "r"(a[2]), "r"(a[3]), "r"(db), "n"(scale_d));
}
__device__ __forceinline__ uint64_t make_desc(uint32_t addr, uint32_t lbo_bytes, uint32_t sbo_bytes) {
  return (uint64_t)((addr & 0x3FFFF) >> 4) | ((uint64_t)(lbo_bytes >> 4) << 16) | ((uint64_t)(sbo_bytes >> 4) << 32) | (1ull << 62);
}

__device__ __forceinline__ void ldsm_x4(uint32_t addr, uint32_t& r0, uint32_t& r1, uint32_t& r2, uint32_t& r3) {
  asm volatile("ldmatrix.sync.aligned.m8n8.x4.shared.b16 {%0,%1,%2,%3}, [%4];" : "=r"(r0), "=r"(r1), "=r"(r2), "=r"(r3) : "r"(addr) : "memory");
}
__device__ __forceinline__ void ldsm_x4_t(uint32_t addr, uint32_t& r0, uint32_t& r1, uint32_t& r2, uint32_t& r3) {
  asm volatile("ldmatrix.sync.aligned.m8n8.x4.trans.shared.b16 {%0,%1,%2,%3}, [%4];" : "=r"(r0), "=r"(r1), "=r"(r2), "=r"(r3) : "r"(addr) : "memory");
}
__device__ __forceinline__ void stsm_x4(uint32_t addr, uint32_t r0, uint32_t r1, uint32_t r2, uint32_t r3) {
  asm volatile("stmatrix.sync.aligned.m8n8.x4.shared.b16 [%0], {%1,%2,%3,%4};" :: "r"(addr), "r"(r0), "r"(r1), "r"(r2), "r"(r3) : "memory");
}
__device__ __forceinline__ void stsm_x4_t(uint32_t addr, uint32_t r0, uint32_t r1, uint32_t r2, uint32_t r3) {
  asm volatile("stmatrix.sync.aligned.m8n8.x4.trans.shared.b16 [%0], {%1,%2,%3,%4};" :: "r"(addr), "r"(r0), "r"(r1), "r"(r2), "r"(r3) : "memory");
}
__device__ __forceinline__ void sts128(uint32_t addr, uint32_t a, uint32_t b, uint32_t c, uint32_t d) {
  asm volatile("st.shared.v4.u32 [%0], {%1,%2,%3,%4};" :: "r"(addr), "r"(a), "r"(b), "r"(c), "r"(d) : "memory");
}
__device__ __forceinline__ float lds32f(uint32_t addr) {
  float v;
  asm volatile("ld.shared.f32 %0, [%1];" : "=f"(v) : "r"(addr) : "memory");
  return v;
}
__device__ __forceinline__ void sts32f(uint32_t addr, float a) {
  asm volatile("st.shared.f32 [%0], %1;" :: "r"(addr), "f"(a) : "memory");
}
__device__ __forceinline__ void mma_bf16(float (&c)[4], uint32_t a0, uint32_t a1, uint32_t a2, uint32_t a3, uint32_t b0, uint32_t b1) {
  asm volatile("mma.sync.aligned.m16n8k16.row.col.f32.bf16.bf16.f32 {%0,%1,%2,%3}, {%4,%5,%6,%7}, {%8,%9}, {%0,%1,%2,%3};"
               : "+f"(c[0]), "+f"(c[1]), "+f"(c[2]), "+f"(c[3]) : "r"(a0), "r"(a1), "r"(a2), "r"(a3), "r"(b0), "r"(b1));
}
__device__ __forceinline__ void mma_bf16_z(float (&c)[4], uint32_t a0, uint32_t a1, uint32_t a2, uint32_t a3, uint32_t b0, uint32_t b1) {
  asm volatile("mma.sync.aligned.m16n8k16.row.col.f32.bf16.bf16.f32 {%0,%1,%2,%3}, {%4,%5,%6,%7}, {%8,%9}, {%10,%10,%10,%10};"
               : "=f"(c[0]), "=f"(c[1]), "=f"(c[2]), "=f"(c[3]) : "r"(a0), "r"(a1), "r"(a2), "r"(a3), "r"(b0), "r"(b1), "f"(0.f));
}
__device__ __forceinline__ uint32_t movm_t(uint32_t v) {
  uint32_t r;
  asm volatile("movmatrix.sync.aligned.m8n8.trans.b16 %0, %1;" : "=r"(r) : "r"(v));
  return r;
}
__device__ __forceinline__ uint32_t pack_bf16(float lo, float hi) {
  uint32_t r;
  asm("cvt.rn.bf16x2.f32 %0, %1, %2;" : "=r"(r) : "f"(hi), "f"(lo));
  return r;
}
__device__ __forceinline__ float bf_lo(uint32_t v) { return __uint_as_float(v << 16); }
__device__ __forceinline__ float bf_hi(uint32_t v) { return __uint_as_float(v & 0xFFFF0000u); }
__device__ __forceinline__ void split3(float x, uint32_t& h, uint32_t& m, uint32_t& l) {
  h = pack_bf16(x, 0.f); x -= bf_lo(h);
  m = pack_bf16(x, 0.f); x -= bf_lo(m);
  l = pack_bf16(x, 0.f);
}
__device__ __forceinline__ float ex2(float x) { float r; asm("ex2.approx.ftz.f32 %0, %1;" : "=f"(r) : "f"(x)); return r; }
__device__ __forceinline__ float rcp_fast(float x) { float r; asm("rcp.approx.ftz.f32 %0, %1;" : "=f"(r) : "f"(x)); return r; }
__device__ __forceinline__ void red_v4(float* p, float a, float b, float c, float d) {
  asm volatile("red.global.add.v4.f32 [%0], {%1, %2, %3, %4};" :: "l"(p), "f"(a), "f"(b), "f"(c), "f"(d) : "memory");
}
__device__ __forceinline__ uint4 ld_ll(const uint4* p) {
  uint4 v;
  asm volatile("{\n.reg .b64 a, b;\nld.relaxed.gpu.global.v2.b64 {a, b}, [%4];\nmov.b64 {%0, %1}, a;\nmov.b64 {%2, %3}, b;\n}\n"
               : "=r"(v.x), "=r"(v.y), "=r"(v.z), "=r"(v.w) : "l"(p) : "memory");
  return v;
}
__device__ __forceinline__ void st_b64(uint2* p, uint32_t a, uint32_t b) {
  asm volatile("{\n.reg .b64 v;\nmov.b64 v, {%1, %2};\nst.relaxed.gpu.global.b64 [%0], v;\n}\n" :: "l"(p), "r"(a), "r"(b) : "memory");
}
__device__ __forceinline__ void st_b128(uint4* p, uint32_t a, uint32_t b, uint32_t c, uint32_t d) {
  asm volatile("{\n.reg .b128 v;\nmov.b128 v, {%1, %2, %3, %4};\nst.relaxed.gpu.global.b128 [%0], v;\n}\n" :: "l"(p), "r"(a), "r"(b), "r"(c), "r"(d) : "memory");
}
__device__ __forceinline__ uint4 ld_b128(const uint4* p) {
  uint4 v;
  asm volatile("{\n.reg .b128 v;\nld.relaxed.gpu.global.b128 v, [%4];\nmov.b128 {%0, %1, %2, %3}, v;\n}\n" : "=r"(v.x), "=r"(v.y), "=r"(v.z), "=r"(v.w) : "l"(p) : "memory");
  return v;
}

constexpr float LOG2E = 1.4426950408889634f;

struct Params {
  const __nv_bfloat16* wA_o;
  const __nv_bfloat16* wB_qkv;
  const __nv_bfloat16* wB_o;
  const unsigned* epoch;
};

#define ACC_DEF(d, n) _Pragma("unroll") for (int i_ = 0; i_ < (n); i_++) asm volatile("" : "=f"(d[i_]))
#define ACC_FENCE(d, n) _Pragma("unroll") for (int i_ = 0; i_ < (n); i_++) asm volatile("" : "+f"(d[i_]) :: "memory")
#define PIN(a, n) _Pragma("unroll") for (int i_ = 0; i_ < (n); i_++) asm volatile("" : "+f"((a)[i_]))
#define PINU(a, n) _Pragma("unroll") for (int i_ = 0; i_ < (n); i_++) asm volatile("" : "+r"((a)[i_]))

#define V_ADDR(p0, sw) uint32_t va_[2] = {(p0) + (srowoff >> 1) + (lhi ^ lsw2 ^ (sw)), (p0) + (srowoff >> 1) + ((32 + lhi) ^ lsw2 ^ (sw))}
#define STAGE_V(acc) { \
    _Pragma("unroll") for (int j_ = 0; j_ < 4; j_++) { \
      const float* a_ = (acc) + j_ * 8; \
      stsm_x4(va_[j_ & 1] + (j_ >> 1) * 8192, \
              pack_bf16(rs0 * a_[0], rs0 * a_[1]), pack_bf16(rs1 * a_[2], rs1 * a_[3]), pack_bf16(rs0 * a_[4], rs0 * a_[5]), pack_bf16(rs1 * a_[6], rs1 * a_[7])); } }
#define FRAG(dst, acc, TR, grp) { \
    _Pragma("unroll") for (int i_ = 15; i_ >= 0; i_--) { \
      const float r_ = (i_ & 8) ? rs1 : rs0; \
      const uint32_t w_ = pack_bf16(r_ * (acc)[4 * (i_ & 7) + (i_ >> 3) * 2], r_ * (acc)[4 * (i_ & 7) + (i_ >> 3) * 2 + 1]); \
      (dst)[8 + i_] = (TR) ? movm_t(w_) : w_; \
      if (i_ == 8 && warp >= 6 && mm < 15) { \
        _Pragma("unroll") for (int j_ = 0; j_ < 2; j_++) \
          st_b128(g_halo + (size_t)(mm * 8 + jj) * 512 + ((grp) * 4 + warp * 2 - 12 + j_) * 32 + lane, ((dst)[16 + j_ * 4] & ~1u) | H_BIT(l), (dst)[17 + j_ * 4], (dst)[18 + j_ * 4], (dst)[19 + j_ * 4]); } } \
    PINU((dst) + 8, 16); }
#define FRAG_PUT(src, slot) if (warp < 6) { _Pragma("unroll") for (int j_ = 0; j_ < 2; j_++) \
      sts128(sbase + OFF_S + (slot) * 8192 + 2048 + warp * 1024 + j_ * 512 + lane * 16, (src)[j_ * 4], (src)[j_ * 4 + 1], (src)[j_ * 4 + 2], (src)[j_ * 4 + 3]); }
#define FRAG_GET(dst, slot) { _Pragma("unroll") for (int j_ = 0; j_ < 2; j_++) \
      asm volatile("ld.shared.v4.u32 {%0, %1, %2, %3}, [%4];" : "=r"((dst)[j_ * 4]), "=r"((dst)[j_ * 4 + 1]), "=r"((dst)[j_ * 4 + 2]), "=r"((dst)[j_ * 4 + 3]) \
                   : "r"(sbase + OFF_S + (slot) * 8192 + warp * 1024 + j_ * 512 + lane * 16) : "memory"); }
#define RW(j) (((j) >> 1) * 4 + ((j) & 1))
template <int POS> __device__ __forceinline__ float exps16_(float* o, const float* p) {
  float s[4];
#pragma unroll
  for (int j = 0; j < 16; j++) { o[j] = ex2(POS ? p[RW(j)] : -p[RW(j)]); if (j < 4) s[j] = o[j]; else s[j & 3] += o[j]; }
  const float r = (s[0] + s[1]) + (s[2] + s[3]);
  return r + __shfl_xor_sync(0xffffffffu, r, 1);
}
template <int POS> __device__ __forceinline__ void exps16_fix(float* o, const float* p, float& sum) {
  if (__builtin_expect(__any_sync(0xffffffffu, !(sum > SUMLO && sum < SUMHI)), 0)) {
    float m = p[0], q[32];
#pragma unroll
    for (int j = 1; j < 16; j++) m = POS ? fmaxf(m, p[RW(j)]) : fminf(m, p[RW(j)]);
    const float x = __shfl_xor_sync(0xffffffffu, m, 1);
    m = POS ? fmaxf(m, x) : fminf(m, x);
#pragma unroll
    for (int j = 0; j < 16; j++) q[RW(j)] = p[RW(j)] - m;
    sum = exps16_<POS>(o, q);
  }
}
__device__ __forceinline__ void store16(const float* e, float sum, uint32_t dst, uint32_t dsw, int c0) {
  const float inv = rcp_fast(sum);
#pragma unroll
  for (int j = 0; j < 2; j++)
    sts128(dst + (((c0 + j) << 4) ^ dsw), pack_bf16(e[j * 8] * inv, e[j * 8 + 1] * inv), pack_bf16(e[j * 8 + 2] * inv, e[j * 8 + 3] * inv),
           pack_bf16(e[j * 8 + 4] * inv, e[j * 8 + 5] * inv), pack_bf16(e[j * 8 + 6] * inv, e[j * 8 + 7] * inv));
}
template <int POS> __device__ __forceinline__ void expp16(uint32_t* o, float* p) {
  {
#pragma unroll
    for (int r = 0; r < 4; r += 2) {
      float m = p[r];
#pragma unroll
      for (int j = 1; j < 8; j++) m = POS ? fmaxf(m, p[r + RW(j)]) : fminf(m, p[r + RW(j)]);
#pragma unroll
      for (int s = 1; s <= 2; s <<= 1) { const float x = __shfl_xor_sync(0xffffffffu, m, s); m = POS ? fmaxf(m, x) : fminf(m, x); }
#pragma unroll
      for (int j = 0; j < 8; j++) p[r + RW(j)] -= m;
    }
  }
#pragma unroll
  for (int j = 0; j < 8; j++) o[j] = pack_bf16(ex2(POS ? p[2 * j] : -p[2 * j]), ex2(POS ? p[2 * j + 1] : -p[2 * j + 1]));
}
__device__ __forceinline__ void scale32(float* o, const float* p, float c0, float c1) {
#pragma unroll
  for (int i = 0; i < 32; i++) asm volatile("mul.f32 %0, %1, %2;" : "=f"(o[i]) : "f"(p[i]), "f"((i & 2) ? c1 : c0));
}
__device__ __forceinline__ bool any_big(const float* p) {
  float m[4];
#pragma unroll
  for (int i = 0; i < 32; i++) m[i >> 3] = (i & 7) ? fmaf(p[i], p[i], m[i >> 3]) : p[i] * p[i];
  return __any_sync(0xffffffffu, !(fmaxf(fmaxf(m[0], m[1]), fmaxf(m[2], m[3])) < BIGLIM));
}
__device__ __forceinline__ void phiq_a(float* p, bool big) {
  if (__builtin_expect(!big, 1)) {
#pragma unroll
    for (int j = 0; j < 16; j++) p[j] = ex2(p[j]);
  }
}
template <int NEXT> __device__ __forceinline__ void phiq_b(uint32_t* o, float* p, bool big) {
  if (__builtin_expect(big, 0)) {
    expp16<0>(o, p); expp16<1>(o + 8, p);
  } else {
    if (NEXT) phiq_a(p + 16, false);
#pragma unroll
    for (int j = 0; j < 4; j++) {
      const float a = p[4 * j], b = p[4 * j + 1], c = p[4 * j + 2], d = p[4 * j + 3];
      const float ab = a * b, cd = c * d, r = rcp_fast(ab * cd), x = r * cd, y = r * ab;
      o[2 * j] = pack_bf16(x * b, x * a); o[2 * j + 1] = pack_bf16(y * d, y * c);
      o[8 + 2 * j] = pack_bf16(a, b); o[9 + 2 * j] = pack_bf16(c, d);
    }
  }
}
#define SCHED_FENCE() asm volatile("pmevent 0;" ::: "memory")

__global__ void __cluster_dims__(2, 1, 1) __launch_bounds__(384, 1)
mega_kernel(const Params prm  , const __grid_constant__ CUtensorMap tm_x0, const __grid_constant__ CUtensorMap tm_xo, const __grid_constant__ CUtensorMap tm_os,
            const __grid_constant__ CUtensorMap tm_o, const __grid_constant__ CUtensorMap tm_wf,
            const __grid_constant__ CUtensorMap tm_wqA, const __grid_constant__ CUtensorMap tm_wqB,
            const __grid_constant__ CUtensorMap tm_woA, const __grid_constant__ CUtensorMap tm_woB,
            const __grid_constant__ CUtensorMap tm_phi) {
  extern __shared__ __align__(1024) uint8_t smem_raw[];
  const uint32_t sbase = smem_u32(smem_raw);
  const uint32_t bar_full = sbase + OFF_BAR;
  const uint32_t bar_done = bar_full + 384;
  const uint32_t bar_stat = bar_full + 768, bar_stat2 = bar_full + 776, bar_epi = bar_full + 784, bar_phi = bar_full + 936  , bar_halo = bar_full + 904  ;
  const uint32_t bar_xr = bar_full + 800, bar_lx = bar_full + 808, bar_stg = bar_full + 832;
  const uint32_t bar_chk = bar_full + 848;

  const int warp = __shfl_sync(0xffffffffu, threadIdx.x >> 5, 0), lane = threadIdx.x & 31;
  const uint32_t bar_kx = sbase + OFF_ID + 384 + warp * 8;
  uint32_t rank;
  asm volatile("mov.u32 %0, %%cluster_ctarank;" : "=r"(rank));
  const int aux = (int)blockIdx.x - NMAIN, tp = (int)(blockIdx.x >> 1) - 4;
  const int gp = tp < 0 ? 0 : (tp < 32 ? tp & 7 : 1 + (tp - 32) % 7), me = tp < 0 ? tp + 8 : (tp < 32 ? tp >> 3 : 4 + (tp - 32) / 7);
  const int jj = me, cc = gp;
  const int cta = aux >= 0 ? -1 : (cc * 8 + jj) * 2 + (int)rank;
  const int mm = cc * 2 + (int)rank;

#define LOAD_EPOCH() const unsigned epoch = ld_relaxed(prm.epoch), ep1 = epoch + 1; (void)epoch
  int budget = 1 << 22;
  unsigned epoch0 = 0;

  if (cta >= 0) {
    if (warp >= 8 && warp < 10 && elect_one()) {
      const int u = warp - 8;
      const uint32_t fb = bar_full + u * 8;
      mbar_init(fb, 1);
      asm volatile("fence.mbarrier_init.release.cluster;" ::: "memory");
      fence_proxy_async_smem();
      mbar_expect_tx(fb, QST + SLOT);
      if (STAG2 && u) __nanosleep(STAG2);
      tma_load_t(sbase + OFF_RA + u * SLOT, &tm_x0, fb, srcb(jj, u) * 128, mm * 128);
#pragma unroll
      for (int i = 0; i < 6; i++) tma_load_2d(sbase + u * QST + i * 4096, &tm_wqA, fb, jj * 128 + (i >> 1) * 1024, srcb(jj, u) * 128 + (i & 1) * 32);
      PROFT(472 + u);
    }
    __syncwarp();
    if (elect_one()) {
#pragma unroll
      for (int i = 0; i < 4; i++) {
        const int u = warp * 4 + i;
        mbar_init(u < 2 ? bar_kx : bar_full + u * 8, ((u >= 4 && u < 11) || (u > 32 && u != 40)) ? 2 : 1); mbar_init(bar_done + u * 8, 16);
      }
      mbar_init(bar_stat + warp * 16, 0x111111181182ull >> (4 * warp) & 15);
      mbar_init(bar_stat + warp * 16 + 8, 0x111111121811ull >> (4 * warp) & 15);
      mbar_init(bar_chk + 112 + (warp & 7) * 8, 1);
      mbar_init(bar_kx, 1);
      asm volatile("fence.mbarrier_init.release.cluster;" ::: "memory");
    }
    __syncwarp();
    if (threadIdx.x == 383) epoch0 = ld_relaxed(prm.epoch);
    if (PRL == 0 && lane == 0 && warp >= 8) PROFT(440 + warp - 8);
    __syncthreads();
    if (PRL == 0 && threadIdx.x == 256) PROFT(444);
    asm volatile("barrier.cluster.arrive.relaxed.aligned;" ::: "memory");
  }

  if (cta < 0) {
    LOAD_EPOCH();
    const uint32_t buf = sbase + warp * SLOT, bar = sbase + OFF_BAR + warp * 16;
    const uint32_t lsw = (lane & 7) << 4, lhi = (lane >> 4) << 4, lrow = (lane & 15) * 128;
    const bool el = elect_one();
    if (el) {
      mbar_init(bar, 1); mbar_init(bar + 8, 1);
      asm volatile("fence.mbarrier_init.release.cluster;" ::: "memory");
    }
#pragma unroll 1
    for (int rd = 0; rd < (NLAYERS > 1 ? 5 : 2); rd++) {
      if (rd >= 2 && warp >= 8) break;
      const int tk = rd < 2 ? aux * 12 + warp : aux * 8 + warp;
      const int half = tk & 1;
      const int blk = rd < 2 ? (tk >> 1) * 2 + rd : (4 - rd) * 16 + (tk >> 1);
      const CUtensorMap* tm = rd < 2 ? &tm_wqA : (rd == 2 ? &tm_wqB : &tm_wf);
      const int j0 = (blk & 15) >> 1;
#define AUX_LOAD(n) { const uint32_t d_ = buf + ((n) & 1) * 8192, b_ = bar + ((n) & 1) * 8; const int r_ = kslice(j0, 2 * ((AUXORD >> (4 * (n))) & 7) + half) * 64; \
        mbar_expect_tx(b_, 8192); tma_load_2d(d_, tm, b_, blk * 64, r_); tma_load_2d(d_ + 4096, tm, b_, blk * 64, r_ + 32); }
      if (el) {
        if (rd == 3) { wait_flag(&g_flags.wfready[j0].v, ep1 * 16); fence_proxy_async_global(); }
        AUX_LOAD(0); AUX_LOAD(1);
      }
      __syncwarp();
      float cs[8][4];
#pragma unroll
      for (int i = 0; i < 8; i++) cs[i][0] = cs[i][1] = cs[i][2] = cs[i][3] = 0.f;
#pragma unroll 1
      for (int n = 0; n < 8; n++) {
        const uint32_t tb = buf + (n & 1) * 8192 + lrow;
        mbar_wait(bar + (n & 1) * 8, (n >> 1) & 1);
#pragma unroll
        for (int i = 0; i < 16; i++) {
          uint32_t b0, b1, b2, b3;
          ldsm_x4_t(tb + (i >> 2) * 2048 + (((i & 3) * 32 + lhi) ^ lsw), b0, b1, b2, b3);
          mma_bf16(cs[2 * (i & 3)], 0x3F803F80u, 0x3F803F80u, 0x3F803F80u, 0x3F803F80u, b0, b1);
          mma_bf16(cs[2 * (i & 3) + 1], 0x3F803F80u, 0x3F803F80u, 0x3F803F80u, 0x3F803F80u, b2, b3);
        }
        __syncwarp();
        if (el && n < 6) AUX_LOAD(n + 2);
        __syncwarp();
      }
      if (lane < 4) {
#pragma unroll
        for (int i = 0; i < 8; i++) st_b64(&g_colsum[rd >= 2][blk * 32 + i * 4 + lane][half], __float_as_uint(cs[i][0]), (__float_as_uint(cs[i][1]) & ~3u) | (ep1 & 3));
      }
      __syncwarp();
    }
  } else if (warp >= 8) {
    asm volatile("setmaxnreg.dec.sync.aligned.u32 40;");
    if (warp == 8) {
      const bool el = elect_one();
      cluster_wait();
      if (el) {
        if (PRL == 0) PROFT(445);
#pragma unroll 1
        for (int l = 0; l < NLAYERS; l++) {
          const uint32_t par = l & 1;
          const CUtensorMap* tqk = par ? &tm_wf : &tm_wqA;
          const CUtensorMap* tv = par ? &tm_wqB : &tm_wqA;
          const CUtensorMap* two = par ? &tm_woB : &tm_woA;
          if (l == 1) { LOAD_EPOCH(); wait_flag(&g_flags.wfready[jj].v, ep1 * 16); fence_proxy_async_global(); }
#pragma unroll 1
          for (int u = l ? 0 : EARLY; u < 32; u++) {
            if (u >= 4) mbar_wait_sl(bar_done + (u - 4) * 8, par);
            else mbar_wait_sl(bar_done + (43 + u + (u >> 1)) * 8, par ^ 1);
            const uint32_t fb = bar_full + u * 8;
            const int v = (l || u > 7) ? u : u - 4;
            const bool res = u < 11 || (u >= 18 && u < 22);
            mbar_expect_tx(fb, res ? QST : QST + SLOT);
            const int row = kslice(jj, v < 4 ? v & 1 : (u < 18 ? u - 2 : (u < 22 ? u - 6 : u - 20))) * 64 + (int)rank * 32;
            const int ps = v < 4 ? v >> 1 : (u >= 18), col = jj * 128 + ps * 64;
            const int c0 = par ? jj * 128 + (ps ? 0 : 1024) : col;
            const uint32_t dst = sbase + (u & 3) * QST + rank * 4096;
            tma_load_2d_mc(dst, tqk, fb, c0, row);
            tma_load_2d_mc(dst + 8192, tqk, fb, c0 + (par ? 64 : 1024), row);
            tma_load_2d_mc(dst + 16384, tv, fb, col + 2048, row);
            if (u < 8) PROFL3(472 + u);
          }
#pragma unroll 1
          for (int s = 0; s < 16; s++) {
            if (s < 5) { if (s != 2 && s != 4) mbar_wait_sl(bar_done + (28 + s) * 8, par); }
            else if (s != 14) mbar_wait_sl(bar_done + (27 + s - (s == 15)) * 8, par);
            const uint32_t fb = bar_full + (32 + s) * 8;
            mbar_expect_tx(fb, SLOT);
            tma_load_2d_mc(sbase + rank * 8192 + (uint32_t)((WO_BSLOT >> (4 * s)) & 15) * SLOT, two, fb, jj * 128 + (int)rank * 64, wslice(jj, s) * 64);
            const int ts = s + 1;
            if (s >= 5 && ts < 8) {
              mbar_expect_tx(bar_chk - 8 + ts * 8, SLOT);
              tma_load_t(sbase + (uint32_t)((WO_ASLOT(par) >> (4 * ts)) & 15) * SLOT, &tm_o, bar_chk - 8 + ts * 8, wslice(jj, ts) * 64, mm * 128);
            }
          }
        }
      }
      __syncwarp();
    } else if (warp == 9) {
      const bool el = elect_one();
      if (el) {
#pragma unroll
        for (int i = 0; i < 2; i++) {
          mbar_expect_tx(bar_full + 32 + i * 8, SLOT);
          mbar_wait_sl(bar_full + (i ? OWNW1 : OWNW0) * 8, 0);
          tma_load_t(sbase + OFF_S + i * SLOT, &tm_x0, bar_full + 32 + i * 8, jj * 128 + i * 64, mm * 128);
        }
      }
      __syncwarp();
      LOAD_EPOCH();
#pragma unroll 1
      for (int lp = 0; lp < 4 * NLAYERS; lp++) {
        const int l = lp >> 2, ph = lp & 3;
        if (ph == 3) continue;
        const uint32_t par = l & 1;
        const unsigned* pp = reinterpret_cast<const unsigned*>(g_obuf + (ph >> 1) * 64 + (size_t)(mm * 128 + (ph ? 0 : S_LEN) + ((lane & 7) | PROWS) * 16 + (jj & 1) * 8) * D_MODEL +
                                                               (jj >> 1) * 16 + srcb(jj, lane >> 3) * 128);
        const CUtensorMap* tm = lp ? &tm_o : &tm_x0;
        const int row = mm * 128 + ((ph || !l) ? 0 : S_LEN);
        const uint32_t bit = ph ? O_BIT(l) : X_BIT(l - 1);
        const uint32_t slots = ph ? (uint32_t)(WO_ASLOT(par) >> (ph * 32 - 28)) : 0x8769876u;
        const unsigned long long fr = ph == 0 ? XPACE : ph == 1 ? (par ? FRB : 0x35351F1E1Dull) : 0x27262524232232ull;
        uint32_t no = (lp == 0 || (lp & 7) == 1) ? 0 : (ph == 1 ? NOB : (ph ? NO1 : NOX)), v0 = 0, v1 = 0;
        mbar_wait_sl(ph ? bar_done + ((uint32_t)fr & 63) * 8 : (l ? bar_done + 47 * 8 : bar_full), ph ? par : (l ? par ^ 1 : 0));
        if (el && ph) PROFT(324 + l * 16 + ph);
        __syncwarp();
        if (no && (ph == 1 ? SPD1 : (ph ? SPD2 : SPD0))) __nanosleep(ph == 1 ? SPD1 : (ph ? SPD2 : SPD0));
        if (no) { v0 = ld_relaxed(pp); if (ph != 1) __nanosleep(POLLGAP); v1 = ld_relaxed(pp); }
#pragma unroll 1
        for (int i = lp ? 0 : 4; i < (ph == 1 ? 5 : 7); i++, no >>= 8) {
          uint32_t op[4] = {(lp ? bar_chk + (ph >> 1) * 112 : bar_full + 32) + i * 8  , sbase + ((slots >> (4 * i)) & 15) * SLOT,
                            (uint32_t)(srcb(jj, i) * 128 + (ph >> 1) * 64), bar_done + ((uint32_t)(fr >> (8 * i)) & 63) * 8};
          PINU(op, 4);
          if (el) mbar_expect_tx(op[0], SLOT);
#pragma unroll 1
          for (int it = 0; (no & 0xFF) && it < (1 << 18); it++) {
            no &= __ballot_sync(0xffffffffu, (v0 ^ bit) & 1) >> (8 * i);
            if (no) v0 = ld_relaxed(pp);
            if (!(no & 0xFF)) break;
            no &= __ballot_sync(0xffffffffu, (v1 ^ bit) & 1) >> (8 * i);
            if (no) v1 = ld_relaxed(pp);
          }
          if (i >= (ph ? 1 : 4)) mbar_wait_sl(op[3], par);
          if (el) {
            if (i == 0) PROFT(320 + l * 16 + ph);
            PROFL3(448 + ph * 8 + i);
            tma_load_t(op[1], tm, op[0], op[2], row);
          }
          __syncwarp();
        }
        if (ph == 0 && el) {
          if (l) { wait_flag(&g_flags.xready[l][mm].v, ep1 * 8); fence_proxy_async_global(); }
#pragma unroll 1
          for (int u = 11; u < 34; u++) {
            if (u == 18) u = 22;
            mbar_wait_sl(bar_done + (u - 4) * 8, par);
            if (u == 32) mbar_expect_tx(bar_xr, 2 * SLOT);
            tma_load_t(sbase + OFF_RA + (u & 3) * SLOT, tm, u < 32 ? bar_full + u * 8 : bar_xr, kslice(jj, u < 18 ? u - 2 : (u < 32 ? u - 20 : u - 32)) * 64, row);
          }
        }
        __syncwarp();
      }
      if (el && atomicAdd(&g_flags.done.v, 1) == ep1 * NMAIN - 1) asm volatile("st.relaxed.gpu.global.u32 [%0], %1;" :: "l"(&g_flags.epoch.v), "r"(ep1) : "memory");
      __syncwarp();
      cluster_wait();
    } else {
      const int hw = warp - 10;
      if (elect_one()) {
        const uint32_t fb = bar_full + 16 + hw * 8;
        mbar_expect_tx(fb, QST + SLOT);
#pragma unroll
        for (int i = 0; i < 6; i++) tma_load_2d(sbase + (2 + hw) * QST + i * 4096, &tm_wqA, fb, jj * 128 + (i >> 1) * 1024, srcb(jj, 2 + hw) * 128 + (i & 1) * 32);
        tma_load_t(sbase + OFF_RA + (2 + hw) * SLOT, &tm_x0, fb, srcb(jj, 2 + hw) * 128, mm * 128);
        mbar_arrive_local(fb + 32);
        if (PRL == 0) PROFT(446 + hw);
      }
      __syncwarp();
      const unsigned epoch = hw ? __shfl_sync(0xffffffffu, epoch0, 31) : ld_relaxed(prm.epoch), ep1 = epoch + 1;
      const bool el = elect_one();
      cluster_wait();
      if (hw == 0) {
        mbar_wait_sl(bar_full + 8, 0);
        if (lane < 7) prefetch_tmap(lane == 0 ? &tm_os : lane == 1 ? &tm_o : lane == 2 ? &tm_wf : lane == 3 ? &tm_wqB : lane == 4 ? &tm_woA : lane == 5 ? &tm_woB : &tm_phi);
#pragma unroll 1
        for (int i = 0; i < (NLAYERS > 1 ? 5 : 0); i++) {
          if (i == 0) mbar_wait_sl(bar_done + FD0 * 8, 0);
          if (el) {
            if (i == 0) { mbar_expect_tx(bar_phi, 2 * SLOT + 8192); tma_load_2d(sbase + OFF_PHI, &tm_phi, bar_phi, 0, jj * 128); }
            else tma_load_2d(sbase + 12 * SLOT - 4096 + i * 4096, &tm_wqB, bar_phi, jj * 128 + ((i - 1) >> 1) * 64, mm * 64 + (~i & 1) * 32);
          }
          __syncwarp();
          __nanosleep(PFGAP);
        }
      } else {
        if (lane < 24) {
          const uint32_t one = (lane & 8) ? 0u : 0x3F80u << ((lane & 1) * 16), w = (lane >> 1) & 3;
          sts128(sbase + OFF_ID + lane * 16, w == 0 ? one : 0u, w == 1 ? one : 0u, w == 2 ? one : 0u, w == 3 ? one : 0u);
        }
#pragma unroll 1
        for (int b = 0; b < 2; b++) {
          float4* z = reinterpret_cast<float4*>(g_kv[b] + (jj * 4) * KVH + mm * (4 * KVH / 16)) + lane;
#pragma unroll
          for (int i = 0; i < 6; i++) z[i * 32] = make_float4(0.f, 0.f, 0.f, 0.f);
        }
#pragma unroll 1
        for (int i = 0; i < 16; i++) {
          const int b = i >> 2;
          const uint32_t v = (b == 0 ? O_BIT(0) : b == 1 ? X_BIT(0) : H_BIT(0)) + 1;
          uint4* p = b < 2 ? reinterpret_cast<uint4*>(g_obuf + (size_t)(b * S_LEN + mm * 128 + (i & 3) * 32 + (lane >> 3) * 8) * D_MODEL + jj * 128 + (b ? 0 : 64)) + (lane & 7)
                           : g_halo + (size_t)(mm * 8 + jj) * 512 + i * 32 + lane;
          *p = make_uint4(v, v, v, v);
        }
        fence_proxy_async_global();
      }
      __syncwarp();
      uint32_t chkp = 0;
#pragma unroll 1
      for (int lp = 0; lp < 8 * NLAYERS; lp++) {
        const int l = lp >> 3, tk = lp & 7, ph = tk ? 2 - hw : 0;
        const uint32_t par = l & 1;
        int lane; asm volatile("mov.u32 %0, %%laneid;" : "=r"(lane));
        if (tk == 5 || (hw && tk == 0 && l)) {
          const uint32_t bit = ph ? O_BIT(l) : X_BIT(l - 1);
          uint32_t slots = ph ? (uint32_t)(WO_ASLOT(par) >> (ph * 32 - 28)) : 0x8769876u;
          const uint32_t a0 = sbase + (lane & 7) * 126 + lane * 4 + (lane & 1) * 14;
#pragma unroll 1
          for (int c = 0; c < 7; c++, slots >>= 4) {
            const uint32_t cb = bar_chk + 112 - hw * 112 + c * 8;
#pragma unroll 1
            for (int it = 0; it < (1 << 12); it++) {
              mbar_wait_sl(cb, (chkp >> c) & 1);
              chkp ^= 1u << c;
              if (el) PROFL3(384 + ph * 8 + c);
              uint32_t bad;
              asm volatile("{\n.reg .b32 w<16>;\n"
                           "ld.shared.u32 w0, [%1 + 0];\n"
                           "ld.shared.u32 w1, [%1 + 1024];\n"
                           "ld.shared.u32 w2, [%1 + 2048];\n"
                           "ld.shared.u32 w3, [%1 + 3072];\n"
                           "ld.shared.u32 w4, [%1 + 4096];\n"
                           "ld.shared.u32 w5, [%1 + 5120];\n"
                           "ld.shared.u32 w6, [%1 + 6144];\n"
                           "ld.shared.u32 w7, [%1 + 7168];\n"
                           "ld.shared.u32 w8, [%1 + 8192];\n"
                           "ld.shared.u32 w9, [%1 + 9216];\n"
                           "ld.shared.u32 w10, [%1 + 10240];\n"
                           "ld.shared.u32 w11, [%1 + 11264];\n"
                           "ld.shared.u32 w12, [%1 + 12288];\n"
                           "ld.shared.u32 w13, [%1 + 13312];\n"
                           "ld.shared.u32 w14, [%1 + 14336];\n"
                           "ld.shared.u32 w15, [%1 + 15360];\n"
                           "lop3.b32 w0, w0, w1, %2, 0x7E;\n"
                           "lop3.b32 w2, w2, w3, %2, 0x7E;\n"
                           "lop3.b32 w4, w4, w5, %2, 0x7E;\n"
                           "lop3.b32 w6, w6, w7, %2, 0x7E;\n"
                           "lop3.b32 w8, w8, w9, %2, 0x7E;\n"
                           "lop3.b32 w10, w10, w11, %2, 0x7E;\n"
                           "lop3.b32 w12, w12, w13, %2, 0x7E;\n"
                           "lop3.b32 w14, w14, w15, %2, 0x7E;\n"
                           "lop3.b32 w0, w0, w2, w4, 0xFE;\nlop3.b32 w6, w6, w8, w10, 0xFE;\nlop3.b32 w0, w0, w12, w14, 0xFE;\nlop3.b32 %0, w0, w6, 1, 0xA8;\n}\n"
                           : "=r"(bad) : "r"(a0 + (slots & 15) * SLOT), "r"(bit) : "memory");
              if (__all_sync(0xffffffffu, bad == 0)) break;
              if (el) {
                fence_proxy_async_smem();
                mbar_expect_tx(cb, SLOT);
                tma_load_t(sbase + (slots & 15) * SLOT, &tm_o, cb, srcb(jj, c) * 128 + (ph >> 1) * 64, mm * 128 + (ph ? 0 : S_LEN));
                RETRY_COUNT();
              }
              __syncwarp();
            }
            if (el) { mbar_arrive_local(bar_full + (c + (ph ? 25 + ph * 8 : 4)) * 8); PROFL3(416 + ph * 8 + c); }
            __syncwarp();
          }
        } else if (hw && (tk & 5) == 1) {
          {
            const int hp = tk >> 1;
            const uint4* src = reinterpret_cast<const uint4*>(g_colsum[par][jj * 64 + hp * 32 + lane]);
            uint32_t bad;
            int it = 0;
            float c[6];
            do {
              bad = 0;
#pragma unroll
              for (int p = 0; p < 3; p++) {
                const uint4 v = ld_ll(src + ((par && p < 2) ? (hp ? -32 : 512) + p * 32 : p * 512));
                bad |= (v.y ^ ep1) | (v.w ^ ep1);
                c[2 * p] = __uint_as_float(v.x) + __uint_as_float(v.z); c[2 * p + 1] = __uint_as_float(v.y) + __uint_as_float(v.w);
              }
              bad &= 3;
              if (bad) __nanosleep(CSGAP);
            } while (bad && ++it < (1 << 16));
#pragma unroll
            for (int p = 0; p < 6; p++) {
              uint32_t h, m, lo;
              split3(c[p], h, m, lo);
              sts128(sbase + OFF_LNB + hp * 4096 + (p >> 1) * 1024 + lane * 32 + (p & 1) * 16, h | (m << 16), h | (lo << 16), h | (m << 16), lo | (m << 16));
            }
            fence_proxy_async_smem();
            __syncwarp();
            if (el) { mbar_arrive_local(hp ? bar_stat2 : bar_stat); if (hp == 0) PROFT(324 + l * 16); }
            __syncwarp();
          }
        } else if (tk == 0) {
          mbar_wait_sl(bar_done + (l ? 24 : 56), par);
          const uint4* sp = reinterpret_cast<const uint4*>(g_stats + (size_t)(mm * 128) * 8) + lane;
          if (el) PROFL3(484);
#pragma unroll 1
          for (int hf = 2 * hw; hf < (l ? 4 : 2 + 2 * hw); hf++) {
            if (NLAYERS > 1 && l == 0 && el) tma_load_2d(sbase + 11 * SLOT + hf * 4096, &tm_wqB, bar_phi, 1024 + jj * 128 + (hf >> 1) * 64, mm * 64 + (hf & 1) * 32);
            __syncwarp();
            uint4 v[4];
            uint32_t bad;
            int it = 0;
            do {
              bad = 0;
#pragma unroll
              for (int i = 0; i < 4; i++) { v[i] = ld_ll(sp + (hf * 4 + i) * 32); bad |= (v[i].y ^ STAT_TAG(l)) | (v[i].w ^ STAT_TAG(l)); }
              bad &= 3;
              if (bad) __nanosleep(200);
            } while (bad && ++it < (1 << 16));
            __syncwarp();
            if (el) PROFL3(480 + hf);
            float mean = 0.f, m2 = 0.f;
#pragma unroll
            for (int i = 0; i < 4; i++) {
              float a = __uint_as_float(v[i].x) + __uint_as_float(v[i].z);
              a += __shfl_xor_sync(0xffffffffu, a, 1); a += __shfl_xor_sync(0xffffffffu, a, 2);
              a *= 0.125f;
              const float e0 = __uint_as_float(v[i].x) - a, e1 = __uint_as_float(v[i].z) - a;
              float q = fmaf(fmaf(e0, e0, e1 * e1), 128.f, __uint_as_float(v[i].y) + __uint_as_float(v[i].w));
              q += __shfl_xor_sync(0xffffffffu, q, 1); q += __shfl_xor_sync(0xffffffffu, q, 2);
              if ((lane & 3) == i) { mean = a; m2 = q; }
            }
            const uint32_t row = hf * 32 + (lane & 3) * 8 + (lane >> 2);
            uint32_t h, m, lo;
            split3(-0.5f * mean, h, m, lo);
            sts128(sbase + OFF_LNA + row * 16, h | (h << 16), m | (h << 16), lo | (m << 16), m | (lo << 16));
            sts32f(sbase + OFF_ST + row * 4, rsqrtf(m2 * (1.f / 1024.f) + 1e-5f));
          }
          if (hw) continue;
          fence_proxy_async_smem();
          __syncwarp();
          if (el) { mbar_arrive_local(bar_stat); PROFT(323 + l * 16); }
          __syncwarp();
#pragma unroll 1
          for (int i = 0; i < 8 - 4 * l; i++) {
            asm volatile("prefetch.global.L2 [%0];" :: "l"(i < 4 ? (l ? prm.wB_o : prm.wA_o) + (size_t)cta * 8192 + i * 2048 + lane * 64
                                                                 : prm.wB_qkv + (size_t)(cta * 8 + (i - 4) * 2 + (lane >> 4)) * 3072 + 2048 + (lane & 15) * 64));
            __nanosleep(PFGAP);
          }
        } else if (lp == 3) {
#pragma unroll 1
          for (int c = 0; c < (NLAYERS > 1 ? 8 : 0); c++) {
            if (!(c & 3)) { asm volatile("bar.sync %0, 288;" :: "r"(BAR_WF + (c >> 2)) : "memory"); fence_proxy_async_smem(); }
            if (el) {
              tma_store_2d(&tm_wf, sbase + 11 * SLOT + c * 4096, (c < 4 ? 1024 : -128) + jj * 128 + (c >> 1) * 64, mm * 64 + (c & 1) * 32);
              if (c == 7) {
                asm volatile("cp.async.bulk.commit_group;\ncp.async.bulk.wait_group.read 0;" ::: "memory");
                mbar_arrive_local(bar_phi + 8);
              } else __nanosleep(WFGAP);
            }
            __syncwarp();
          }
          if (el) { bulk_commit_wait(); signal_release(&g_flags.wfready[jj].v); PROFT(335); }
          __syncwarp();
        } else if (tk == 2 || tk == 4) {
          if (par) continue;
          const int i = tk >> 2;
          mbar_wait_sl(bar_done + (i ? HW1 : (hw ? 19 : HW0)) * 8, 0);
          const uint4* src = g_halo + (size_t)(mm * 8 + jj - 8) * 512 + i * 256 + hw * 128 + lane;
          uint4 v[4];
          int it = 0;
          bool ok;
          do {
#pragma unroll
            for (int j = 0; j < 4; j++) v[j] = mm ? ld_b128(src + j * 32) : make_uint4(H_BIT(l), 0, 0, 0);
            ok = __all_sync(0xffffffffu, (((v[0].x ^ H_BIT(l)) | (v[1].x ^ H_BIT(l)) | (v[2].x ^ H_BIT(l)) | (v[3].x ^ H_BIT(l))) & 1) == 0);
          } while (!ok && ++it < (1 << 16));
#pragma unroll
          for (int j = 0; j < 4; j++) sts128(sbase + OFF_S + hw * 8192 + j * 512 + lane * 16, v[j].x, v[j].y, v[j].z, v[j].w);
          __syncwarp();
          if (el) { mbar_arrive_local(bar_halo + hw * 8); PROFT(331 + l * 16 + i * 2 + hw); }
          __syncwarp();
        } else if (tk == 6 && hw == 0 && l < NLAYERS - 1) {
          bar_sync<BAR_X1, 288>();
          if (el) {
            PROFT(328 + l * 16);
            mbar_wait_sl(bar_full + XD * 8, par ^ 1);
            tma_store_t(&tm_o, sbase + 11 * SLOT, jj * 128 + 64, mm * 128 + S_LEN);
            bulk_commit_wait();
            signal_release(&g_flags.xready[l + 1][mm].v);
            PROFT(330 + l * 16);
          }
          __syncwarp();
        }
      }
    }
    cluster_sync();
  } else {
    asm volatile("setmaxnreg.inc.sync.aligned.u32 232;");
    const int wg = warp >> 2;
    const int r0 = warp * 16;
    const uint32_t pK = sbase + OFF_S, pV = sbase + OFF_S + SLOT;
#define PMASKS(on, bit) const uint32_t pm0 = ((on) && t == (g >> 1)), pbit = (bit)
#define PBIT(w) (((w) & ~pm0) | (pbit & pm0))
#define LANE_CONSTS() \
    int lane; asm volatile("mov.u32 %0, %%laneid;" : "=r"(lane)); \
    const int g = lane >> 2, t = lane & 3; \
    const uint32_t srowoff = (r0 + (lane & 15)) * 128, lsw = (lane & 7) << 4, lhi = (lane >> 4) << 4, lsw2 = (lane & 6) << 3; \
    (void)g; (void)t; (void)srowoff; (void)lsw; (void)lhi; (void)lsw2;
    uint32_t stgp = 0, peer;
    asm volatile("mapa.shared::cluster.u32 %0, %1, %2;" : "=r"(peer) : "r"(sbase), "r"(rank ^ 1));
    peer -= sbase;
    const uint32_t dA0 = (((sbase & 0x3FFFF) + wg * 8192) >> 4) | 0x10000u, dB0 = ((sbase & 0x3FFFF) >> 4) | 0x2000000u;
#define DESC(lo, hi) ((uint64_t)(uint32_t)(lo) | ((uint64_t)(hi) << 32))
#define STG_ARRIVE() { __syncwarp(); if (elect_one()) mbar_arrive_local(bar_stg); }
#define STG_WAIT() { mbar_wait(bar_stg, stgp); stgp ^= 1; }
#define PROFS() do {} while (0)
#define REL(addr) { if (elect_one()) { mbar_arrive_local(addr); asm volatile("mbarrier.arrive.shared::cluster.b64 _, [%0];" :: "r"((addr) + peer) : "memory"); } }
#define QSTEP(ACC, DA, SC) { \
      const uint32_t da = (DA), db = dB0 + (ub & 0x18) * (QST >> 7); \
      mbar_wait(ub, par); \
      wgmma_fence(); \
      wgmma4_n192<SC>(ACC, da, db); \
      wgmma_commit(); PROFS(); }
#define QREL() { wgmma_wait<1>(); REL(ub + 376); ub += 8; }
#define RA_CUR (dA0 + (OFF_RA >> 4) + (ub & 0x18) * (SLOT >> 7))
#define PUMP1() { QSTEP(S1, RA_CUR, 1); QREL(); }
#define PUMPN() { wgmma_fence(); wgmma4_n192<1>(S1, RA_CUR, dB0 + (ub & 0x18) * (QST >> 7)); wgmma_commit(); PROFS(); QREL(); }
#define PUMP0() { PUMP1(); SCHED_FENCE(); }
#define WSTEP() { \
      const uint32_t s4 = (ub - bar_full - 256) >> 1; \
      const uint32_t da = dA0 + (((uint32_t)(WO_ASLOT(par) >> s4) & 15) << 10), db = dB0 + (((uint32_t)(WO_BSLOT >> s4) & 15) << 10); \
      mbar_wait(ub, par); \
      wgmma_fence(); \
      wgmma4_n128<1>(S1, da, db); \
      wgmma_commit(); PROFS(); \
      wgmma_wait<1>(); \
      if (s4) REL(ub + 376); \
      ub += 8; }
#define PUMPS(n) { _Pragma("unroll 1") for (int i_ = 0; i_ < (n); i_++) PUMP1(); }
#define LNSTEP(ACC, hh) { wgmma_fence(); wgmma_n192<1, 0>(ACC, make_desc(sbase + OFF_LNA + wg * 1024, 0, 128) ^ (1ull << 62), make_desc(sbase + OFF_LNB + (hh) * 4096, 0, 128) ^ (1ull << 62)); }
#define WARP_STORE(tm, tile, col, row) { fence_proxy_async_smem(); __syncwarp(); WARP_STORE0(tm, tile, col, row); }
#define WARP_STORE0(tm, tile, col, row) { \
      if (elect_one()) { tma_store_2d(tm, (tile) + r0 * 128, col, (row) + r0); asm volatile("cp.async.bulk.commit_group;" ::: "memory"); } __syncwarp(); }
#define TILE_CONSTS(base, on, bit) \
      uint32_t ta[5]; \
      { PMASKS(on, bit); (void)pbit; ta[4] = pm0; } \
      _Pragma("unroll") for (int j = 0; j < 4; j++) ta[j] = (base) + srowoff + ((((uint32_t)j << 5) + lhi) ^ lsw); \
      PINU(ta, 5); SCHED_FENCE(); \
      const uint32_t pm0 = ta[4], pbit = (bit)
#define X_OUT(pc, W) { \
      _Pragma("unroll") for (int j = 0; j < 4; j++) \
        stsm_x4(ta[j] + (pc) * SLOT, \
                PBIT(pack_bf16((W)[j * 8 + 0], (W)[j * 8 + 1])), PBIT(pack_bf16((W)[j * 8 + 2], (W)[j * 8 + 3])), \
                (pack_bf16((W)[j * 8 + 4], (W)[j * 8 + 5])), (pack_bf16((W)[j * 8 + 6], (W)[j * 8 + 7]))); }
#define REST_P1(SKEW) { \
      mbar_wait(bar_stat2, par); \
      LNSTEP(S1, 1); \
      wgmma_commit(); \
      _Pragma("unroll 1") while (ub < bar_full + 256) { \
        const bool hold = ub == bar_full + 256 - 8 * (SKEW) && wg == 0; \
        if (hold) { wgmma_wait<0>(); REL(ub + 376); bar_sync<BAR_SKEW, 256>(); } \
        QSTEP(S1, RA_CUR, 1); \
        if (ub == bar_full + 248 && wg == 1) bar_arrive<BAR_SKEW, 256>(); \
        wgmma_wait<1>(); if (!hold) REL(ub + 376); ub += 8; \
      } \
      mbar_wait(bar_done + (31 - (SKEW)) * 8, par);        \
      wgmma_wait<0>(); \
      ACC_FENCE(S1, 96); \
      REL(bar_done + 31 * 8); \
      PROF(13); }
#define FOLD(tile, rd) { \
          LANE_CONSTS(); \
          float d[32]; \
          ACC_DEF(d, 32); \
          mbar_wait(bar_phi, 0); \
          wgmma_fence(); \
          _Pragma("unroll") for (int i = 0; i < 2; i++) { \
            const uint64_t da = make_desc((tile) + wg * 8192 + i * 64, 16, 1024); \
            const uint64_t db = make_desc(sbase + OFF_PHI + wg * 4096 + i * 2048, 16, 512) ^ (3ull << 62); \
            wgmma_n32<0>(d + i * 16, da, db); wgmma_n32<1>(d + i * 16, da + 2, db + 64); \
          } \
          wgmma_commit(); \
          PUMP0(); \
          ACC_FENCE(d, 32); \
          bar_wg(wg); \
          _Pragma("unroll") for (int i = 0; i < 4; i++) { \
            const float* x = d + (i & 1) * 8 + (i >> 1) * 2; \
            if (rd) sts128((tile) + wg * 8192 + ((warp & 3) * 16 + (i >> 1) * 8 + g) * 128 + (((2 * t + (i & 1)) ^ g) << 4), \
                           pack_bf16(x[0], x[1]), pack_bf16(x[4], x[5]), pack_bf16(x[16], x[17]), pack_bf16(x[20], x[21])); \
            else stsm_x4((tile) + srowoff + ((((uint32_t)i << 5) + lhi) ^ lsw), pack_bf16(d[i * 8], d[i * 8 + 1]), pack_bf16(d[i * 8 + 2], d[i * 8 + 3]), \
                         pack_bf16(d[i * 8 + 4], d[i * 8 + 5]), pack_bf16(d[i * 8 + 6], d[i * 8 + 7])); \
          } \
          }
#define XM_ISSUE() { mbar_wait(bar_xr, par); wgmma_fence(); \
      wgmma_copy(T_, dA0 + (OFF_RA >> 4), make_desc(sbase + OFF_ID, 128, 128) ^ (1ull << 62)); }
#define COPYN(d, s, n) _Pragma("unroll") for (int i_ = 0; i_ < (n); i_++) { uint32_t c_; asm volatile("mov.b32 %0, %1;" : "=r"(c_) : "f"((s)[i_])); (d)[i_] = __uint_as_float(c_); }
#define COPY64(d, s) COPYN(d, s, 64)
#define XM_DONE() { ACC_FENCE(T_, 64); COPY64(S1, T_); ACC_FENCE(S1, 64); \
      __syncwarp(); if (elect_one()) mbar_arrive_local(bar_lx); }
#define LOAD_X() { float T_[64]; ACC_DEF(T_, 64); wgmma_wait<0>(); XM_ISSUE(); wgmma_commit(); wgmma_wait<0>(); XM_DONE(); }

    float S0[96], S1[96];
    if (lane == 0) epoch0 = ld_relaxed(prm.epoch);
    __syncwarp();
    uint32_t ub = bar_full;
    {
      constexpr int l = 0;
      constexpr uint32_t par = 0;
      (void)l;
      ACC_DEF(S0, 96);
      QSTEP(S0, RA_CUR, 0);
      PROF(0);
      SCHED_FENCE();
      cluster_wait();
      ub += 8;
#pragma unroll 1
      for (int i = 1; i < 5; i++) {
        QSTEP(S0, dA0 + (OFF_RA >> 4) + i * (SLOT >> 4), 1);
        QREL();
      }
    }
    const unsigned epoch = __shfl_sync(0xffffffffu, epoch0, 0), ep1 = epoch + 1;
#pragma unroll 1
    for (int l = 0;; l++) {
      const uint32_t par = l & 1;
      PROF(1);
      {
        LANE_CONSTS();
        uint32_t ta[4];
#pragma unroll
        for (int j = 0; j < 4; j++) ta[j] = pK + srowoff + ((((uint32_t)j << 5) + lhi) ^ lsw);
        float p0, p1, a0 = 0.f, a1 = 0.f, q0 = 0.f, q1 = 0.f;
#define STATS(j0, j1) _Pragma("unroll") for (int j = (j0); j < (j1); j++) { \
          uint32_t x[4]; \
          ldsm_x4(ta[j & 3] + (j >> 2) * SLOT, x[0], x[1], x[2], x[3]); \
          if (j == 0) { p0 = __shfl_sync(0xffffffffu, bf_lo(x[0]), lane & 28); p1 = __shfl_sync(0xffffffffu, bf_lo(x[1]), lane & 28); } \
          _Pragma("unroll") for (int i = 0; i < 4; i += 2) { \
            const float d0 = bf_lo(x[i]) - p0, d1 = bf_hi(x[i]) - p0, d2 = bf_lo(x[i + 1]) - p1, d3 = bf_hi(x[i + 1]) - p1; \
            a0 += d0 + d1; a1 += d2 + d3; \
            q0 = fmaf(d1, d1, fmaf(d0, d0, q0)); q1 = fmaf(d3, d3, fmaf(d2, d2, q1)); } } \
          asm volatile("" : "+f"(a0), "+f"(a1), "+f"(q0), "+f"(q1), "+f"(p0), "+f"(p1)); SCHED_FENCE()
        if (SB0) { STATS(0, SB0); }
        bar_wg(wg);
        QSTEP(S0, dA0 + ((OFF_S + SLOT) >> 4), 1);
        QREL();
        SCHED_FENCE();
        STATS(SB0, SB1);
        ACC_DEF(S1, 96);
        QSTEP(S1, dA0 + (OFF_S >> 4), 0);
        QREL();
        SCHED_FENCE();
        STATS(SB1, SB2);
        QSTEP(S1, dA0 + ((OFF_S + SLOT) >> 4), 1);
        QREL();
        SCHED_FENCE();
        STATS(SB2, 8);
#pragma unroll
        for (int o = 1; o <= 2; o <<= 1) {
          a0 += __shfl_xor_sync(0xffffffffu, a0, o); a1 += __shfl_xor_sync(0xffffffffu, a1, o);
          q0 += __shfl_xor_sync(0xffffffffu, q0, o); q1 += __shfl_xor_sync(0xffffffffu, q1, o);
        }
        if (t == 1) { a0 = a1; q0 = q1; p0 = p1; }
        if (t < 2) st_b64(g_stats + (size_t)(mm * 128 + r0 + g + t * 8) * 8 + jj, __float_as_uint(fmaf(a0, 1.f / 128.f, p0)),
                          (__float_as_uint(fmaxf(fmaf(a0 * (-1.f / 128.f), a0, q0), 0.f)) & ~3u) | STAT_TAG(l));
        if (l) { asm volatile("cp.async.bulk.wait_group 0;" ::: "memory"); bar_arrive<BAR_X1, 288>(); }
#pragma unroll 1
        while (ub < bar_full + 144) {
          QSTEP(S0, RA_CUR, 1);
          if (ub == bar_full + 64) PROF(2);
          QREL();
        }
      }
      LANE_CONSTS();
      mbar_wait(bar_stat, par);
      LNSTEP(S0, 0);
      wgmma_commit();
      const float rs0 = lds32f(sbase + OFF_ST + (r0 + g) * 4), rs1 = lds32f(sbase + OFF_ST + (r0 + g + 8) * 4);
      PUMP0();
      ACC_FENCE(S0, 96);
      PROF(3);
      if (!par) {
        constexpr uint32_t par = 0;
        uint32_t qa[16];
        uint32_t kf[24], vf[24];
#define DRAIN_A(ACC, hp, PMP) { \
          LANE_CONSTS(); \
          FRAG(kf, ACC + 32, 0, (hp) * 2); \
          PMP; \
          FRAG(vf, ACC + 64, 1, (hp) * 2 + 1); \
          _Pragma("unroll") for (int i_ = 0; i_ < 16; i_++) qa[i_] = pack_bf16(ACC[2 * i_], ACC[2 * i_ + 1]); \
          PINU(qa, 16); }
        DRAIN_A(S0, 0, PUMP0());
        if (l == 0 && NLAYERS > 1) {
#pragma unroll 1
          for (int rd = 1; rd >= 0; rd--) {
            FOLD(sbase + (12 - rd) * SLOT, rd);
            asm volatile("bar.arrive %0, 288;" :: "r"(BAR_WF + 1 - rd) : "memory");
          }
        }
        PUMPS(FPUMP);
#pragma unroll 1
        for (int h = 0; h < 2; h++) {
          PROFH(4, 16);
          LANE_CONSTS();
          FRAG_PUT(kf + 16, 0); FRAG_PUT(vf + 16, 1);
          STG_ARRIVE();
          if (h) { PROF(8); LOAD_X(); PROF(9); WSTEP(); PROF(10); } else PUMPS(HPUMP2);
          const bool gt0 = 2 * t > g, gt1 = 2 * t >= g;
          uint32_t msk[2] = {(gt0 ? 0xFFFFu : 0u) | (gt1 ? 0xFFFF0000u : 0u), g == 2 * t ? 0x10001u : 0u};
          PINU(msk, 2);
          TILE_CONSTS(sbase, false, 0);
          (void)pm0; (void)pbit;
          if (h) PROF(12);
          STG_WAIT();
          if (h) PROF(14);
          if (warp < 2) mbar_wait(bar_halo, h);
          if (h) PROF(15);
          if (h == 0) mbar_wait(ub, par);
          FRAG_GET(kf, 0);
          PROFH(5, 17);
          float s[2][3][4];
#pragma unroll
          for (int ks = 0; ks < 2; ks++)
#pragma unroll
            for (int i = 0; i < 6; i++) {
              const int hh = i & 1, jb = 2 - (i >> 1);
              const uint32_t* b = kf + jb * 8 + hh * 4 + ks * 2;
              if (ks) mma_bf16(s[hh][jb], qa[hh * 8 + 4], qa[hh * 8 + 5], qa[hh * 8 + 6], qa[hh * 8 + 7], b[0], b[1]);
              else mma_bf16_z(s[hh][jb], qa[hh * 8], qa[hh * 8 + 1], qa[hh * 8 + 2], qa[hh * 8 + 3], b[0], b[1]);
            }
          if (h == 0) PUMPN()
          PROFH(6, 18);
          float va[2][2], vb[2][2], mx[2][2];
#pragma unroll
          for (int hh = 0; hh < 2; hh++) {
            va[hh][0] = gt0 ? s[hh][0][0] : s[hh][1][0];
            vb[hh][0] = gt1 ? s[hh][0][1] : s[hh][1][1];
            va[hh][1] = gt0 ? s[hh][1][2] : s[hh][2][2];
            vb[hh][1] = gt1 ? s[hh][1][3] : s[hh][2][3];
          }
          if (warp < 2 && mm == 0) {
#pragma unroll
            for (int hh = 0; hh < 2; hh++) { if (gt0) va[hh][0] = -INFINITY; if (gt1) vb[hh][0] = -INFINITY; }
          }
#pragma unroll
          for (int i = 0; i < 4; i++) mx[i >> 1][i & 1] = fmaxf(va[i >> 1][i & 1], vb[i >> 1][i & 1]);
#pragma unroll
          for (int o = 1; o <= 2; o <<= 1)
#pragma unroll
            for (int i = 0; i < 4; i++) mx[i >> 1][i & 1] = fmaxf(mx[i >> 1][i & 1], __shfl_xor_sync(0xffffffffu, mx[i >> 1][i & 1], o));
          const float sc0 = rs0 * (0.17677669529663687f * LOG2E), sc1 = rs1 * (0.17677669529663687f * LOG2E);
#pragma unroll
          for (int i = 0; i < 4; i++) {
            const float sc = (i & 1) ? sc1 : sc0, m = mx[i >> 1][i & 1];
            va[i >> 1][i & 1] = ex2((va[i >> 1][i & 1] - m) * sc); vb[i >> 1][i & 1] = ex2((vb[i >> 1][i & 1] - m) * sc);
            mx[i >> 1][i & 1] = va[i >> 1][i & 1] + vb[i >> 1][i & 1];
          }
          if (h == 0) { PIN(&va[0][0], 4); PIN(&vb[0][0], 4); PIN(&mx[0][0], 4); PUMP1(); }
          if (h) PROF(20);
          if (warp < 2) mbar_wait(bar_halo + 8, h);
          if (h) PROF(21);
          if (h == 0) mbar_wait(ub, par);
          FRAG_GET(vf, 1);
#pragma unroll
          for (int o = 1; o <= 2; o <<= 1)
#pragma unroll
            for (int i = 0; i < 4; i++) mx[i >> 1][i & 1] += __shfl_xor_sync(0xffffffffu, mx[i >> 1][i & 1], o);
          float o[8][4];
          uint32_t pa[4][2];
#pragma unroll
          for (int i = 0; i < 4; i++) {
            const float iv = rcp_fast(mx[i >> 1][i & 1]);
            const uint32_t w = pack_bf16(va[i >> 1][i & 1] * iv, vb[i >> 1][i & 1] * iv);
            pa[i][0] = w & msk[0]; pa[i][1] = w & ~msk[0];
          }
          PROFH(7, 19);
#pragma unroll
          for (int i = 7; i >= 0; i--) {
            const uint32_t* a = vf + (i >> 2) * 8 + (i & 3) * 2;
            mma_bf16_z(o[i], a[0], a[1], a[8], a[9], pa[(i & 2) + (i >> 2)][0], pa[(i & 2) + (i >> 2)][1]);
          }
          if (h == 0) PUMPN() else mbar_wait(bar_done + 30 * 8, par);
          if (NLAYERS > 1 && l + h == 0) mbar_wait(bar_phi + 8, 0);
          if (h) PROF(22);
          {
            const uint32_t pm0 = msk[1], pbit = O_BIT(l) * 0x10001u;
#pragma unroll
            for (int i = 0; i < 4; i++)
              stsm_x4_t(ta[i] + (h ? 3 : 12) * SLOT, PBIT(pack_bf16(o[i][0], o[i][1])), PBIT(pack_bf16(o[i + 4][0], o[i + 4][1])),
                        pack_bf16(o[i][2], o[i][3]), pack_bf16(o[i + 4][2], o[i + 4][3]));
          }
          WARP_STORE(&tm_os, sbase + (h ? 3 : 12) * SLOT, jj * 128 + h * 64, mm * 128);
          PROFH(11, 23);
          if (h) break;
          REST_P1(ASKEW);
          asm volatile("cp.async.bulk.wait_group.read 0;" ::: "memory");
          DRAIN_A(S1, 1, {});
        }
      } else {
        constexpr uint32_t par = 1;
        float st[32];
        const float c0 = rs0 * LOG2E, c1 = rs1 * LOG2E;
        { V_ADDR(pV, 0); STAGE_V(S0 + 64); }
        if (warp < 2) sts128(sbase + OFF_ONES + warp * 512 + lane * 16, 0x3F803F80u, 0x3F803F80u, 0x3F803F80u, 0x3F803F80u);
        scale32(st, S0, c0, c1);
        PIN(st, 32);
#define PHI_PIECE(c) { \
          e_[2 * (c)] = ex2(st[2 * (c)]); e_[2 * (c) + 1] = ex2(st[2 * (c) + 1]); \
          _Pragma("unroll") for (int k_ = 4 * (c); k_ < 4 * (c) + 4; k_++) m_[(c) >> 1] = (k_ & 7) ? fmaf(st[k_], st[k_], m_[(c) >> 1]) : st[k_] * st[k_]; \
          asm volatile("" : "+f"(e_[2 * (c)]), "+f"(e_[2 * (c) + 1]), "+f"(m_[(c) >> 1])); SCHED_FENCE(); }
#define PHI_FIN() { \
          big = __any_sync(0xffffffffu, !(fmaxf(fmaxf(m_[0], m_[1]), fmaxf(m_[2], m_[3])) < BIGLIM)); \
          if (__builtin_expect(big, 0)) { COPYN(e_, st, 16); } \
          _Pragma("unroll") for (int k_ = 0; k_ < 16; k_++) st[k_] = e_[k_]; \
          PIN(st, 16); }
#define KV_MMA(vs, IL) { \
          const uint32_t dp = dA0 + 12 * 1024 - wg * 2560, dv = dA0 + (vs) * 1024 + ((OFF_ONES - (vs) * SLOT - 16) << 12) - wg * (512 << 16); \
          STG_WAIT(); \
          fence_proxy_async_smem(); \
          wgmma_fence(); \
          _Pragma("unroll") for (int ks = 0; ks < 8; ks++) { \
            const uint64_t a = DESC(dp + ks * 128, 0x40000040), b = DESC(dv + ks * (64 - (64 << 16)), 0x80000020); \
            if ((IL) && ks) wgmma_fence(); \
            if (ks == 0) wgmma_n40<0, 1>(kv, a, b); else wgmma_n40<1, 1>(kv, a, b); \
            if (ks == 7) wgmma_commit(); \
            if (IL) PHI_PIECE(ks); } }
#define KV_RED1(i) if (h) red_v4(g_kv[l >> 1] + (jj * 4) * KVH + warp * 768 + lane * 4 + (i) * 128, S0[32 + (i) * 3], S0[33 + (i) * 3], S0[34 + (i) * 3], 1.f)
#define KV_REDS(n) { _Pragma("unroll") for (int i_ = 0; i_ < 6; i_++) if (((RPACE >> (4 * i_)) & 15) == (n)) KV_RED1(i_); }
#define KV_SEND(kp) { \
          float sd[9]; \
          _Pragma("unroll") for (int i = 0; i < 8; i++) { (kp)[i] = kv[i]; sd[i] = kv[8 + i]; } \
          (kp)[8] = rank ? kv[18] : kv[16]; sd[8] = rank ? kv[16] : kv[18]; \
          const uint32_t ra = sbase + peer + (warp * 32 + lane) * 4, rb = bar_kx + peer; \
          if (elect_one()) mbar_expect_tx(bar_kx, 1152); \
          _Pragma("unroll") for (int i = 0; i < 2; i++) \
            asm volatile("st.async.weak.shared::cluster.mbarrier::complete_tx::bytes.v4.f32 [%0], {%1, %2, %3, %4}, [%5];" \
                         :: "r"(ra + (warp * 32 + lane) * 12 + OFF_PHI + i * 4096), "f"(sd[4 * i]), "f"(sd[4 * i + 1]), "f"(sd[4 * i + 2]), "f"(sd[4 * i + 3]), "r"(rb) : "memory"); \
          asm volatile("st.async.weak.shared::cluster.mbarrier::complete_tx::bytes.f32 [%0], %1, [%2];" :: "r"(ra + OFF_LNB), "f"(sd[8]), "r"(rb) : "memory"); }
#define KV_RECV(kp, hp) { \
          float r_[9]; \
          float* kvg = g_kv[l >> 1] + (jj * 4 + (hp) * 2) * KVH + warp * 768 + rank * 384 + lane * 4; \
          mbar_wait(bar_kx, l >> 1); \
          _Pragma("unroll") for (int i = 0; i < 2; i++) \
            asm volatile("ld.shared.v4.f32 {%0, %1, %2, %3}, [%4];" : "=f"(r_[4 * i]), "=f"(r_[4 * i + 1]), "=f"(r_[4 * i + 2]), "=f"(r_[4 * i + 3]) \
                         : "r"(sbase + OFF_PHI + i * 4096 + (warp * 32 + lane) * 16) : "memory"); \
          r_[8] = lds32f(sbase + OFF_LNB + (warp * 32 + lane) * 4); \
          _Pragma("unroll") for (int i = 0; i < 3; i++) red_v4(kvg + i * 128, (kp)[3 * i] + r_[3 * i], (kp)[3 * i + 1] + r_[3 * i + 1], (kp)[3 * i + 2] + r_[3 * i + 2], 2.f); }
#define KV_LOAD(hp) { \
          const uint4* kvg = reinterpret_cast<const uint4*>(g_kv[l >> 1] + (jj * 4 + (hp) * 2) * KVH) + warp * 192 + lane; \
          _Pragma("unroll") for (int i = 0; i < 6; i++) v[i] = ld_b128(kvg + i * 32); }
#define KVV(i) __uint_as_float((i) % 3 == 0 ? v[(i) / 3].x : ((i) % 3 == 1 ? v[(i) / 3].y : v[(i) / 3].z))
#define KV_TILE(hp) { \
          _Pragma("unroll 1") for (int it = 0; it < (1 << 16); it++) { \
            if (__all_sync(0xffffffffu, (v[0].w & v[1].w & v[2].w & v[3].w & v[4].w & v[5].w) == 0x41800000u)) break; \
            RETRY_COUNT(); \
            KV_LOAD(hp); \
          } \
          if (hp) PROF(26); else PROF(25); \
          const uint32_t e = lane & 7, jt = ((lane >> 1) & 4) + (e >> 1); \
          const uint32_t row = ((((warp >> 1) ^ wg) & 1) << 5) + ((jt & 1) << 4) + ((warp & 1) << 3) + (jt & 6) + (e & 1); \
          const uint32_t kd = pV + wg * 8192 + row * 128, ksw = (row & 7) << 4; \
          _Pragma("unroll") for (int i = 0; i < 2; i++) \
            stsm_x4(kd + ((i * 32 + lhi) ^ ksw), pack_bf16(KVV(i * 9), KVV(i * 9 + 1)), pack_bf16(KVV(i * 9 + 2), KVV(i * 9 + 3)), \
                    pack_bf16(KVV(i * 9 + 4), KVV(i * 9 + 5)), pack_bf16(KVV(i * 9 + 6), KVV(i * 9 + 7))); \
          stsm_x4(kd + ((64u + lhi) ^ ksw), pack_bf16(KVV(8), 1.f), pack_bf16(KVV(17), 1.f), 0u, 0u); }
#pragma unroll 1
        for (int h = 0; h < 2; h++) {
          PROFH(4, 6);
          PUMP0();
          LANE_CONSTS();
          const uint32_t dsw = (uint32_t)(g ^ (2 * t)) << 4, dst = ((t & 2) ? pK : sbase + 12 * SLOT) + (r0 + g) * 128;
          float e[16], f[16];
          KV_REDS(1);
          float sa = exps16_<0>(e, st);
          exps16_fix<0>(e, st, sa);
          asm volatile("" : "+f"(sa)); PIN(e, 16); PUMP0();
          if (h) STG_WAIT();
          KV_REDS(2);
          store16(e, sa, dst, dsw, 4);
          float sb = exps16_<1>(f, st);
          exps16_fix<1>(f, st, sb);
          asm volatile("" : "+f"(sb)); PIN(f, 16); PUMP0();
          KV_REDS(3);
          store16(f, sb, dst, dsw, 0);
          float sc = exps16_<0>(e, st + 2);
          exps16_fix<0>(e, st + 2, sc);
          asm volatile("" : "+f"(sc)); PIN(e, 16); PUMP0();
          KV_REDS(4);
          store16(e, sc, dst + 1024, dsw, 4);
          float sd = exps16_<1>(f, st + 2);
          exps16_fix<1>(f, st + 2, sd);
          asm volatile("" : "+f"(sd)); PIN(f, 16); PUMP0();
          store16(f, sd, dst + 1024, dsw, 0);
          PROFH(5, 7);
          if (h) break;
          {
            float kv[20];
            ACC_DEF(kv, 20);
            STG_ARRIVE();
            float e_[16], m_[4];
            KV_MMA(11, 0);
            PUMP0();
            ACC_FENCE(kv, 20);
            STG_ARRIVE();
            scale32(st, S0 + 32, c0, c1);
            PIN(st, 32);
            {
              COPYN(S0 + 32, kv, 8); COPYN(S0 + 40, kv + 16, 1); COPYN(S0 + 41, kv + 8, 8); COPYN(S0 + 49, kv + 18, 1);
              const int h = 1;
              KV_REDS(0);
            }
          }
        }
        bool big;
        uint4 v[6];
        {
          float kv[20];
          { LANE_CONSTS(); KV_LOAD(0); }
          mbar_wait(bar_stat2, par);
          ub = bar_full + 240;
          LNSTEP(S1, 1);
          PUMP1();
          if (wg == 0) bar_sync<BAR_SKEW, 256>();
          QSTEP(S1, RA_CUR, 1);
          if (wg == 1) bar_arrive<BAR_SKEW, 256>();
          QREL();
          { LANE_CONSTS(); KV_TILE(0); }
          LANE_CONSTS();
          V_ADDR(sbase + 3 * SLOT, rank * 32);
          PINU(va_, 2);
          mbar_wait(bar_done + 30 * 8, par);
          wgmma_wait<0>();
          ACC_FENCE(S1, 96);
          PROF(13);
          STAGE_V(S1 + 64);
          STG_ARRIVE();
          REL(bar_done + 31 * 8);
          scale32(st, S1, c0, c1);
          PIN(st, 32);
          PROF(16);
          ACC_DEF(kv, 20);
          float e_[16], m_[4];
          KV_MMA(3, 1);
          SCHED_FENCE();
          PROF(14);
          PHI_FIN();
          SCHED_FENCE();
          PROF(15);
          wgmma_wait<0>();
          ACC_FENCE(kv, 20);
          PROF(12);
          { float kp[9]; KV_SEND(kp); _Pragma("unroll") for (int i = 0; i < 3; i++) v[i] = make_uint4(__float_as_uint(kp[3 * i]), __float_as_uint(kp[3 * i + 1]), __float_as_uint(kp[3 * i + 2]), 0u); }
#define VDEF(i0) _Pragma("unroll") for (int i = (i0); i < 6; i++) asm volatile("" : "=r"(v[i].x), "=r"(v[i].y), "=r"(v[i].z), "=r"(v[i].w))
          VDEF(3);
          PROF(17);
        }
#pragma unroll 1
        for (int h = 0; h < 2; h++) {
          const uint32_t pO = sbase + (h ? 3 : 8) * SLOT;
          LANE_CONSTS();
          uint32_t fq[32];
          if (h) { KV_LOAD(1); phiq_a(st, big); PIN(st, 16); PROF(31); }
          PROFH(18, 32);
          SCHED_FENCE();
          phiq_b<1>(fq, st, big); PINU(fq, 16); PIN(st + 16, 16);
          SCHED_FENCE();
          PROFH(8, 9);
          if (h) {
            asm volatile("cp.async.bulk.wait_group.read 0;" ::: "memory");
            mbar_wait(bar_lx, par);
            PROF(30);
            KV_TILE(1);
            STG_ARRIVE();
          }
          SCHED_FENCE();
          if (h == 0) {
            float kp[9];
#pragma unroll
            for (int i = 0; i < 9; i++) kp[i] = KVV(i);
            KV_RECV(kp, 1);
            SCHED_FENCE();
          }
          phiq_b<0>(fq + 16, st + 16, big); PINU(fq + 16, 16);
          PROFH(10, 21);
          if (h) { STG_WAIT(); fence_proxy_async_smem(); }
          wgmma_wait<0>();
          ACC_FENCE(S1, 64);
          PROFH(19, 33);
          float o[4][20];
#define O_MMA(hh) { \
            const uint64_t db = make_desc(pV + (hh) * 8192, 16, 1024); \
            ACC_DEF(o[(hh) * 2], 20); ACC_DEF(o[(hh) * 2 + 1], 20); \
            wgmma_fence(); \
            wgmma_n40_rs<0>(o[(hh) * 2], fq + (hh) * 16, db + 256); wgmma_n40_rs<0>(o[(hh) * 2 + 1], fq + (hh) * 16 + 8, db); \
            wgmma_n40_rs<1>(o[(hh) * 2], fq + (hh) * 16 + 4, db + 384); wgmma_n40_rs<1>(o[(hh) * 2 + 1], fq + (hh) * 16 + 12, db + 128); \
            wgmma_commit(); }
          O_MMA(0);
          SCHED_FENCE();
          PMASKS(true, O_BIT(l));
#pragma unroll
          for (int hh = 0; hh < 2; hh++) {
            wgmma_wait<0>();
            ACC_FENCE(o[hh * 2], 20); ACC_FENCE(o[hh * 2 + 1], 20);
            if (!hh) { O_MMA(1); SCHED_FENCE(); }
            if (hh) PROFH(22, 24);
            const float* x = o[hh * 2];
            const float* y = o[hh * 2 + 1];
            const float sx0 = x[17] * 0x1p-40f, sy0 = y[17] * 0x1p-40f, sx1 = x[19] * 0x1p-40f, sy1 = y[19] * 0x1p-40f;
            const float i0 = rcp_fast(fmaf(fmaf(x[17], 1e-6f, x[16]), sy0, y[16] * sx0)), i1 = rcp_fast(fmaf(fmaf(x[19], 1e-6f, x[18]), sy1, y[18] * sx1));
            const float ax0 = sy0 * i0, ay0 = sx0 * i0, ax1 = sy1 * i1, ay1 = sx1 * i1;
#pragma unroll
            for (int dp = 0; dp < 2; dp++)
              stsm_x4(pO + srowoff + ((hh * 64 + dp * 32 + lhi) ^ lsw),
                      PBIT(pack_bf16(fmaf(x[dp * 8], ax0, y[dp * 8] * ay0), fmaf(x[dp * 8 + 1], ax0, y[dp * 8 + 1] * ay0))),
                      PBIT(pack_bf16(fmaf(x[dp * 8 + 2], ax1, y[dp * 8 + 2] * ay1), fmaf(x[dp * 8 + 3], ax1, y[dp * 8 + 3] * ay1))),
                      (pack_bf16(fmaf(x[dp * 8 + 4], ax0, y[dp * 8 + 4] * ay0), fmaf(x[dp * 8 + 5], ax0, y[dp * 8 + 5] * ay0))),
                      (pack_bf16(fmaf(x[dp * 8 + 6], ax1, y[dp * 8 + 6] * ay1), fmaf(x[dp * 8 + 7], ax1, y[dp * 8 + 7] * ay1))));
          }
          WARP_STORE(&tm_os, pO, jj * 128 + h * 64, mm * 128);
          PROFH(20, 34);
          if (h) break;
          float T_[64];
          scale32(st, S1 + 32, c0, c1);
          PIN(st, 32);
          ACC_DEF(T_, 64);
          XM_ISSUE(); wgmma_commit();
          SCHED_FENCE();
          big = any_big(st);
          SCHED_FENCE();
          PROF(27);
          wgmma_wait<0>(); XM_DONE();
          PROF(28);
          bar_wg(wg);
          WSTEP();
          SCHED_FENCE();
          VDEF(0);
          PROF(29);
        }
      }
      __syncwarp();
      if (elect_one()) mbar_arrive_local(bar_epi);
      bar_wg(wg);
#pragma unroll 1
      while (ub < bar_full + 384) {
        WSTEP();
        if (ub == bar_full + 8 * 41) { asm volatile("cp.async.bulk.wait_group.read 0;" ::: "memory"); PROF(35); }
        if (ub == bar_full + 8 * 42) PROF(36);
      }
      {
        float Wb[32];
        LANE_CONSTS();
        TILE_CONSTS(pK, l < NLAYERS - 1, X_BIT(l));
        if (l < NLAYERS - 1) mbar_wait(bar_full, par ^ 1);
        wgmma_wait<0>();
        ACC_FENCE(S1, 64);
        COPYN(Wb, S1 + 32, 32);
        PROF(37);
        uint32_t xa[16];
#pragma unroll
        for (int i = 0; i < 16; i++) { const uint32_t w = pack_bf16(S1[2 * i], S1[2 * i + 1]); xa[i] = (i & 2) ? w : PBIT(w); }
        PINU(xa, 16);
#define XA_OUT() _Pragma("unroll") for (int j = 0; j < 4; j++) stsm_x4(ta[j], xa[4 * j], xa[4 * j + 1], xa[4 * j + 2], xa[4 * j + 3])
        if (l == NLAYERS - 1) {
          XA_OUT();
          int w; asm volatile("mov.u32 %0, %1;" : "=r"(w) : "r"(warp));
          const int oc = jj * 128 + (w & 1) * 1024, orow = mm * 64 + (w >> 1) * 16 - r0;
          WARP_STORE(&tm_xo, pK, oc, orow);
          { PMASKS(false, 0); X_OUT(1, Wb); }
          WARP_STORE(&tm_xo, pV, oc + 64, orow);
          break;
        }
        PROF(38);
        XA_OUT();
        ACC_DEF(S0, 96);
        wgmma_fence();
        wgmma_n192_rs<0>(S0, xa, dB0);
#pragma unroll
        for (int k = 1; k < RSK; k++) wgmma_n192_rs<1>(S0, xa + 4 * k, dB0 + 128 * k);
        wgmma_commit();
        WARP_STORE(&tm_os, pK, jj * 128, mm * 128 + S_LEN);
        if (RSK < 4) {
          wgmma_fence();
#pragma unroll
          for (int k = RSK; k < 4; k++) wgmma_n192_rs<1>(S0, xa + 4 * k, dB0 + 128 * k);
          wgmma_commit();
        }
        { const int ln_ = l + 1, l = ln_; const uint32_t ub = bar_full; (void)l; (void)ub; PROFS(); }
        REL(bar_done + 47 * 8);
        ub = bar_full + 8;
        PROF(39);
        { PMASKS(false, 0); X_OUT(1, Wb); }
        fence_proxy_async_smem();
      }
    }
    asm volatile("cp.async.bulk.wait_group.read 0;" ::: "memory");
    cluster_sync();
  }
}

typedef CUresult (*PFN_encode)(CUtensorMap*, CUtensorMapDataType, cuuint32_t, void*, const cuuint64_t*, const cuuint64_t*,
                               const cuuint32_t*, const cuuint32_t*, CUtensorMapInterleave, CUtensorMapSwizzle,
                               CUtensorMapL2promotion, CUtensorMapFloatOOBfill);

CUtensorMap make_map(PFN_encode enc, const void* ptr, uint64_t inner, uint64_t outer, uint32_t box_inner, uint32_t box_outer,
                     CUtensorMapSwizzle swz = CU_TENSOR_MAP_SWIZZLE_128B, int promo = CU_TENSOR_MAP_L2_PROMOTION_L2_256B) {
  CUtensorMap m;
  cuuint64_t dims[2] = {inner, outer};
  cuuint64_t strides[1] = {inner * 2};
  cuuint32_t box[2] = {box_inner, box_outer};
  cuuint32_t es[2] = {1, 1};
  enc(&m, CU_TENSOR_MAP_DATA_TYPE_BFLOAT16, 2, const_cast<void*>(ptr), dims, strides, box, es, CU_TENSOR_MAP_INTERLEAVE_NONE,
      swz, (CUtensorMapL2promotion)promo, CU_TENSOR_MAP_FLOAT_OOB_FILL_NONE);
  return m;
}

CUtensorMap make_tile_map(PFN_encode enc, const void* ptr, uint64_t rows, bool by_parity, int promo) {
  CUtensorMap m;
  cuuint64_t dims[4] = {D_MODEL, 16, 2, rows / 32};
  cuuint64_t strides[3] = {by_parity ? 4096u : 2048u, by_parity ? 2048u : 32768u, 65536};
  cuuint32_t box[4] = {64, 16, 2, 4};
  cuuint32_t es[4] = {1, 1, 1, 1};
  enc(&m, CU_TENSOR_MAP_DATA_TYPE_BFLOAT16, 4, const_cast<void*>(ptr), dims, strides, box, es, CU_TENSOR_MAP_INTERLEAVE_NONE,
      CU_TENSOR_MAP_SWIZZLE_128B, (CUtensorMapL2promotion)promo, CU_TENSOR_MAP_FLOAT_OOB_FILL_NONE);
  return m;
}

}

extern "C" void kernel_launch(void* const* d_in, const int* in_sizes, int n_in, void* d_out, int out_size) {
  (void)in_sizes; (void)n_in; (void)out_size;
  static PFN_encode enc = nullptr;
  if (!enc) {
    void* fn = nullptr;
    cudaDriverEntryPointQueryResult qr;
    cudaGetDriverEntryPoint("cuTensorMapEncodeTiled", &fn, cudaEnableDefault, &qr);
    enc = (PFN_encode)fn;
    cudaFuncSetAttribute(mega_kernel, cudaFuncAttributeMaxDynamicSharedMemorySize, SMEM_BYTES);
  }
  Params prm;
  prm.wA_o = (const __nv_bfloat16*)d_in[2];
  prm.wB_qkv = (const __nv_bfloat16*)d_in[4];
  prm.wB_o = (const __nv_bfloat16*)d_in[6];
  void *obuf = nullptr, *wf = nullptr, *fl = nullptr;
  cudaGetSymbolAddress(&fl, g_flags);
  prm.epoch = &static_cast<Flags*>(fl)->epoch.v;
  cudaGetSymbolAddress(&obuf, g_obuf);
  cudaGetSymbolAddress(&wf, g_wfold);
  CUtensorMap tm_x0 = make_tile_map(enc, d_in[0], S_LEN, true, XPROMO);
  CUtensorMap tm_xo = make_map(enc, d_out, 2 * D_MODEL, S_LEN / 2, 64, 16);
  CUtensorMap tm_os = make_map(enc, obuf, D_MODEL, 2 * S_LEN, 64, 16);
  CUtensorMap tm_o = make_tile_map(enc, obuf, 2 * S_LEN, false, OPROMO);
  CUtensorMap tm_wf = make_map(enc, wf, 2048, D_MODEL, 64, 32);
  CUtensorMap tm_wqA = make_map(enc, d_in[1], 3 * D_MODEL, D_MODEL, 64, 32, CU_TENSOR_MAP_SWIZZLE_128B, WPROMO);
  CUtensorMap tm_wqB = make_map(enc, prm.wB_qkv, 3 * D_MODEL, D_MODEL, 64, 32);
  CUtensorMap tm_woA = make_map(enc, prm.wA_o, D_MODEL, D_MODEL, 64, 64);
  CUtensorMap tm_woB = make_map(enc, prm.wB_o, D_MODEL, D_MODEL, 64, 64);
  CUtensorMap tm_phi = make_map(enc, d_in[5], 32, 1024, 32, 128, CU_TENSOR_MAP_SWIZZLE_64B);
  mega_kernel<<<NMAIN + NAUX, 384, SMEM_BYTES>>>(prm, tm_x0, tm_xo, tm_os, tm_o, tm_wf, tm_wqA, tm_wqB, tm_woA, tm_woB, tm_phi);
}
```

```cpp
#include <cuda_runtime.h>
#include <cuda.h>
#include <cuda_bf16.h>
#include <stdint.h>

#define NLAYERS 4

#define HPUMP2 1
#define ASKEW 2
#define FPUMP 3
#define PFGAP 100
#define POLLGAP 120
#define HW1 30
#define XPACE 0x06050401000000ull
#define HW0 18
#define XD 4
#define WFGAP 10
#define EARLY 4
#define BIGLIM 3600.f
#define SUMLO 0x1p-100f
#define SUMHI 0x1p100f
#define XPROMO 2
#define OPROMO 3
#define STAG2 0
#define WPROMO 3
#define SB0 2
#define SB1 4
#define SB2 6
#define PROWS 7
#define SPD0 0
#define SPD1 0
#define SPD2 300
#define FRB 0x3535353535ull
#define NOB 0xFFFFFF00u
#define NO1 ~0u
#define NOX ~0u
#define FD0 3
#define CSGAP 300
#define AUXORD 0x76543210
#define FSK 3
#define OWNW0 1
#define OWNW1 2
#define RPACE 0x221100
#define RSK 2
namespace {

constexpr int S_LEN = 2048, D_MODEL = 1024;
constexpr int NAUX = 4, NMAIN = 128;
constexpr int SLOT = 16384;
constexpr int QST = 24576;
constexpr int OFF_RA = 6 * SLOT, OFF_S = 10 * SLOT;
constexpr int OFF_HALO = 13 * SLOT, OFF_LNB = OFF_HALO  , OFF_ONES = OFF_HALO + 3072;
constexpr int OFF_ST = OFF_HALO + 7168  , OFF_ID = OFF_HALO + 7680, OFF_PHI = OFF_HALO + 8192;
constexpr int OFF_BAR = 14 * SLOT;
constexpr int OFF_LNA = OFF_BAR + 1024;
constexpr int SMEM_BYTES = OFF_LNA + 2048;
#define WO_ASLOT(par) ((par) ? 0x9876CAB39876CA98ull : 0xBC7698A3BC7698BCull)
constexpr unsigned long long WO_BSLOT = 0x5432105421054210ull;
__device__ __forceinline__ int srcb(int j, int i) { return (i + (i >= j)) & 7; }
__device__ __forceinline__ int kslice(int j, int i) { return i < 2 ? 2 * j + i : (i < 9 ? 2 * srcb(j, i - 2) : 2 * srcb(j, i - 9) + 1); }
__device__ __forceinline__ int wslice(int j, int s) { return 2 * ((s & 7) ? srcb(j, (s & 7) - 1) : j) + (s >> 3); }
constexpr int KVH = 6 * 128 * 4;

struct __align__(128) Flag { unsigned v; unsigned pad[31]; };
struct Flags {
  Flag xready[4][16];
  Flag wfready[8];
  Flag done;
  Flag epoch;
};

__device__ Flags g_flags;
__device__ __nv_bfloat16 g_obuf[2 * S_LEN * D_MODEL];
#define O_BIT(l) ((epoch * NLAYERS + (l) + 1) & 1u)
#define X_BIT(l) ((epoch * (NLAYERS - 1) + (l) + 1) & 1u)
__device__ __nv_bfloat16 g_wfold[D_MODEL * 2048];
__device__ uint4 g_halo[16 * 8 * 512];
__device__ __align__(128) float g_kv[2][32 * KVH];
__device__ __align__(128) uint2 g_colsum[2][1536][2];
__device__ __align__(128) uint2 g_stats[S_LEN * 8];
#define H_BIT(l) (NLAYERS > 2 ? (uint32_t)((l) == 0) : (ep1 & 1))
#define STAT_TAG(l) ((ep1 * NLAYERS + (l) + 1) & 3u)

#define RETRY_COUNT()
#define PRL 3
#define PROFL 1
#define PROFW 0
#define PROFT(i) do {} while (0)
#define PROF(i) do {} while (0)
#define PROFH(i, j) do {} while (0)
#define PROFL3(i) do {} while (0)

__device__ __forceinline__ uint32_t smem_u32(const void* p) { return (uint32_t)__cvta_generic_to_shared(p); }
__device__ __forceinline__ bool elect_one() {
  uint32_t p;
  asm volatile("{\n.reg .pred p;\nelect.sync _|p, 0xffffffff;\nselp.u32 %0, 1, 0, p;\n}\n" : "=r"(p));
  return p != 0;
}
__device__ __forceinline__ void mbar_init(uint32_t bar, uint32_t cnt) {
  asm volatile("mbarrier.init.shared::cta.b64 [%0], %1;" :: "r"(bar), "r"(cnt));
}
__device__ __forceinline__ void mbar_expect_tx(uint32_t bar, uint32_t bytes) {
  asm volatile("mbarrier.arrive.expect_tx.shared::cta.b64 _, [%0], %1;" :: "r"(bar), "r"(bytes) : "memory");
}
#define mbar_wait(bar, parity) \
  asm volatile("{\n.reg .pred p, q;\nW_%=:\nmbarrier.try_wait.parity.shared::cta.b64 p, [%1], %2;\nadd.s32 %0, %0, -1;\n" \
               "setp.gt.and.s32 q, %0, 0, !p;\n@q bra.uni W_%=;\n}\n" : "+r"(budget) : "r"((uint32_t)(bar)), "r"((uint32_t)(parity)) : "memory")
#define mbar_wait_sl(bar, parity) \
  asm volatile("{\n.reg .pred p, q;\nW_%=:\nmbarrier.try_wait.parity.shared::cta.b64 p, [%1], %2, 20000;\nadd.s32 %0, %0, -64;\n" \
               "setp.gt.and.s32 q, %0, 0, !p;\n@q bra.uni W_%=;\n}\n" : "+r"(budget) : "r"((uint32_t)(bar)), "r"((uint32_t)(parity)) : "memory")
__device__ __forceinline__ void mbar_arrive_local(uint32_t bar) {
  asm volatile("mbarrier.arrive.shared::cta.b64 _, [%0];" :: "r"(bar) : "memory");
}
__device__ __forceinline__ void tma_load_2d(uint32_t dst, const CUtensorMap* tm, uint32_t bar, int c0, int c1) {
  asm volatile("cp.async.bulk.tensor.2d.shared::cluster.global.mbarrier::complete_tx::bytes [%0], [%1, {%3, %4}], [%2];"
               :: "r"(dst), "l"(tm), "r"(bar), "r"(c0), "r"(c1) : "memory");
}
__device__ __forceinline__ void tma_load_2d_mc(uint32_t dst, const CUtensorMap* tm, uint32_t bar, int c0, int c1) {
  asm volatile("cp.async.bulk.tensor.2d.shared::cluster.global.mbarrier::complete_tx::bytes.multicast::cluster [%0], [%1, {%3, %4}], [%2], %5;"
               :: "r"(dst), "l"(tm), "r"(bar), "r"(c0), "r"(c1), "h"((uint16_t)3) : "memory");
}
__device__ __forceinline__ void tma_store_2d(const CUtensorMap* tm, uint32_t src, int c0, int c1) {
  asm volatile("cp.async.bulk.tensor.2d.global.shared::cta.bulk_group [%0, {%2, %3}], [%1];"
               :: "l"(tm), "r"(src), "r"(c0), "r"(c1) : "memory");
}
__device__ __forceinline__ void tma_load_t(uint32_t dst, const CUtensorMap* tm, uint32_t bar, int c0, int row) {
  asm volatile("cp.async.bulk.tensor.4d.shared::cluster.global.mbarrier::complete_tx::bytes [%0], [%1, {%3, %5, %5, %4}], [%2];"
               :: "r"(dst), "l"(tm), "r"(bar), "r"(c0), "r"(row >> 5), "r"(0) : "memory");
}
__device__ __forceinline__ void tma_store_t(const CUtensorMap* tm, uint32_t src, int c0, int row) {
  asm volatile("cp.async.bulk.tensor.4d.global.shared::cta.bulk_group [%0, {%2, %4, %4, %3}], [%1];"
               :: "l"(tm), "r"(src), "r"(c0), "r"(row >> 5), "r"(0) : "memory");
}
__device__ __forceinline__ void bulk_commit_wait() {
  asm volatile("cp.async.bulk.commit_group;\ncp.async.bulk.wait_group 0;" ::: "memory");
}
__device__ __forceinline__ void prefetch_tmap(const CUtensorMap* tm) {
  asm volatile("prefetch.tensormap [%0];" :: "l"(tm) : "memory");
}
__device__ __forceinline__ void fence_proxy_async_global() { asm volatile("fence.proxy.async.global;" ::: "memory"); }
__device__ __forceinline__ void fence_proxy_async_smem() { asm volatile("fence.proxy.async.shared::cta;" ::: "memory"); }
__device__ __forceinline__ unsigned ld_relaxed(const unsigned* p) {
  unsigned v;
  asm volatile("ld.relaxed.gpu.global.u32 %0, [%1];" : "=r"(v) : "l"(p) : "memory");
  return v;
}
__device__ __forceinline__ void fence_acquire() { asm volatile("fence.acquire.gpu;" ::: "memory"); }
__device__ __forceinline__ void wait_flag(const unsigned* p, unsigned target) {
  int it = 0;
  while ((int)(ld_relaxed(p) - target) < 0 && ++it < (1 << 20)) {}
  fence_acquire();
}
__device__ __forceinline__ void signal_release(unsigned* p) {
  asm volatile("red.release.gpu.global.add.u32 [%0], 1;" :: "l"(p) : "memory");
}
template <int ID, int N> __device__ __forceinline__ void bar_arrive() { asm volatile("bar.arrive %0, %1;" :: "n"(ID), "n"(N) : "memory"); }
template <int ID, int N> __device__ __forceinline__ void bar_sync() { asm volatile("bar.sync %0, %1;" :: "n"(ID), "n"(N) : "memory"); }
__device__ __forceinline__ void bar_wg(int wg) { asm volatile("bar.sync %0, 128;" :: "r"(2 + wg) : "memory"); }
__device__ __forceinline__ void cluster_sync() {
  asm volatile("barrier.cluster.arrive.relaxed.aligned;\nbarrier.cluster.wait.aligned;" ::: "memory");
}
__device__ __forceinline__ void cluster_wait() { asm volatile("barrier.cluster.wait.acquire.aligned;" ::: "memory"); }
enum { BAR_X1 = 7, BAR_WF = 8  , BAR_SKEW = 10 };

__device__ __forceinline__ void wgmma_fence() { asm volatile("wgmma.fence.sync.aligned;" ::: "memory"); }
__device__ __forceinline__ void wgmma_commit() { asm volatile("wgmma.commit_group.sync.aligned;" ::: "memory"); }
template <int N> __device__ __forceinline__ void wgmma_wait() { asm volatile("wgmma.wait_group.sync.aligned %0;" :: "n"(N) : "memory"); }

template <int scale_d, int tnsp_b = 1> __device__ __forceinline__ void wgmma_n192(float* d, uint64_t descA, uint64_t descB) {
  asm volatile("{\n.reg .pred p;\nsetp.ne.b32 p, %98, 0;\n"
               "wgmma.mma_async.sync.aligned.m64n192k16.f32.bf16.bf16 {%0,%1,%2,%3,%4,%5,%6,%7,%8,%9,%10,%11,%12,%13,%14,%15,%16,%17,%18,%19,%20,%21,%22,%23,%24,%25,%26,%27,%28,%29,%30,%31,%32,%33,%34,%35,%36,%37,%38,%39,%40,%41,%42,%43,%44,%45,%46,%47,%48,%49,%50,%51,%52,%53,%54,%55,%56,%57,%58,%59,%60,%61,%62,%63,%64,%65,%66,%67,%68,%69,%70,%71,%72,%73,%74,%75,%76,%77,%78,%79,%80,%81,%82,%83,%84,%85,%86,%87,%88,%89,%90,%91,%92,%93,%94,%95}, %96, %97, p, 1, 1, 0, %99;\n}\n"
               : "+f"(d[0]), "+f"(d[1]), "+f"(d[2]), "+f"(d[3]), "+f"(d[4]), "+f"(d[5]), "+f"(d[6]), "+f"(d[7]), "+f"(d[8]), "+f"(d[9]), "+f"(d[10]), "+f"(d[11]), "+f"(d[12]), "+f"(d[13]), "+f"(d[14]), "+f"(d[15]), "+f"(d[16]), "+f"(d[17]), "+f"(d[18]), "+f"(d[19]), "+f"(d[20]), "+f"(d[21]), "+f"(d[22]), "+f"(d[23]), "+f"(d[24]), "+f"(d[25]), "+f"(d[26]), "+f"(d[27]), "+f"(d[28]), "+f"(d[29]), "+f"(d[30]), "+f"(d[31]), "+f"(d[32]), "+f"(d[33]), "+f"(d[34]), "+f"(d[35]), "+f"(d[36]), "+f"(d[37]), "+f"(d[38]), "+f"(d[39]), "+f"(d[40]), "+f"(d[41]), "+f"(d[42]), "+f"(d[43]), "+f"(d[44]), "+f"(d[45]), "+f"(d[46]), "+f"(d[47]), "+f"(d[48]), "+f"(d[49]), "+f"(d[50]), "+f"(d[51]), "+f"(d[52]), "+f"(d[53]), "+f"(d[54]), "+f"(d[55]), "+f"(d[56]), "+f"(d[57]), "+f"(d[58]), "+f"(d[59]), "+f"(d[60]), "+f"(d[61]), "+f"(d[62]), "+f"(d[63]), "+f"(d[64]), "+f"(d[65]), "+f"(d[66]), "+f"(d[67]), "+f"(d[68]), "+f"(d[69]), "+f"(d[70]), "+f"(d[71]), "+f"(d[72]), "+f"(d[73]), "+f"(d[74]), "+f"(d[75]), "+f"(d[76]), "+f"(d[77]), "+f"(d[78]), "+f"(d[79]), "+f"(d[80]), "+f"(d[81]), "+f"(d[82]), "+f"(d[83]), "+f"(d[84]), "+f"(d[85]), "+f"(d[86]), "+f"(d[87]), "+f"(d[88]), "+f"(d[89]), "+f"(d[90]), "+f"(d[91]), "+f"(d[92]), "+f"(d[93]), "+f"(d[94]), "+f"(d[95])
               : "l"(descA), "l"(descB), "n"(scale_d), "n"(tnsp_b));
}
template <int scale_d> __device__ __forceinline__ void wgmma4_n192(float* d, uint32_t da, uint32_t db) {
#define R_ "{%0,%1,%2,%3,%4,%5,%6,%7,%8,%9,%10,%11,%12,%13,%14,%15,%16,%17,%18,%19,%20,%21,%22,%23,%24,%25,%26,%27,%28,%29,%30,%31,%32,%33,%34,%35,%36,%37,%38,%39,%40,%41,%42,%43,%44,%45,%46,%47,%48,%49,%50,%51,%52,%53,%54,%55,%56,%57,%58,%59,%60,%61,%62,%63,%64,%65,%66,%67,%68,%69,%70,%71,%72,%73,%74,%75,%76,%77,%78,%79,%80,%81,%82,%83,%84,%85,%86,%87,%88,%89,%90,%91,%92,%93,%94,%95}"
  asm volatile("{\n.reg .pred p, q;\n.reg .b64 a, b;\nsetp.ne.b32 p, %98, 0;\nsetp.eq.b32 q, 0, 0;\nmov.b64 a, {%96, 0x40000040};\nmov.b64 b, {%97, 0x40000040};\n"
               "wgmma.mma_async.sync.aligned.m64n192k16.f32.bf16.bf16 " R_ ", a, b, p, 1, 1, 0, 1;\nadd.s64 a, a, 2;\nadd.s64 b, b, 128;\n"
               "wgmma.mma_async.sync.aligned.m64n192k16.f32.bf16.bf16 " R_ ", a, b, q, 1, 1, 0, 1;\nadd.s64 a, a, 2;\nadd.s64 b, b, 128;\n"
               "wgmma.mma_async.sync.aligned.m64n192k16.f32.bf16.bf16 " R_ ", a, b, q, 1, 1, 0, 1;\nadd.s64 a, a, 2;\nadd.s64 b, b, 128;\n"
               "wgmma.mma_async.sync.aligned.m64n192k16.f32.bf16.bf16 " R_ ", a, b, q, 1, 1, 0, 1;\n}\n"
               : "+f"(d[0]), "+f"(d[1]), "+f"(d[2]), "+f"(d[3]), "+f"(d[4]), "+f"(d[5]), "+f"(d[6]), "+f"(d[7]), "+f"(d[8]), "+f"(d[9]), "+f"(d[10]), "+f"(d[11]), "+f"(d[12]), "+f"(d[13]), "+f"(d[14]), "+f"(d[15]), "+f"(d[16]), "+f"(d[17]), "+f"(d[18]), "+f"(d[19]), "+f"(d[20]), "+f"(d[21]), "+f"(d[22]), "+f"(d[23]), "+f"(d[24]), "+f"(d[25]), "+f"(d[26]), "+f"(d[27]), "+f"(d[28]), "+f"(d[29]), "+f"(d[30]), "+f"(d[31]), "+f"(d[32]), "+f"(d[33]), "+f"(d[34]), "+f"(d[35]), "+f"(d[36]), "+f"(d[37]), "+f"(d[38]), "+f"(d[39]), "+f"(d[40]), "+f"(d[41]), "+f"(d[42]), "+f"(d[43]), "+f"(d[44]), "+f"(d[45]), "+f"(d[46]), "+f"(d[47]), "+f"(d[48]), "+f"(d[49]), "+f"(d[50]), "+f"(d[51]), "+f"(d[52]), "+f"(d[53]), "+f"(d[54]), "+f"(d[55]), "+f"(d[56]), "+f"(d[57]), "+f"(d[58]), "+f"(d[59]), "+f"(d[60]), "+f"(d[61]), "+f"(d[62]), "+f"(d[63]), "+f"(d[64]), "+f"(d[65]), "+f"(d[66]), "+f"(d[67]), "+f"(d[68]), "+f"(d[69]), "+f"(d[70]), "+f"(d[71]), "+f"(d[72]), "+f"(d[73]), "+f"(d[74]), "+f"(d[75]), "+f"(d[76]), "+f"(d[77]), "+f"(d[78]), "+f"(d[79]), "+f"(d[80]), "+f"(d[81]), "+f"(d[82]), "+f"(d[83]), "+f"(d[84]), "+f"(d[85]), "+f"(d[86]), "+f"(d[87]), "+f"(d[88]), "+f"(d[89]), "+f"(d[90]), "+f"(d[91]), "+f"(d[92]), "+f"(d[93]), "+f"(d[94]), "+f"(d[95])
               : "r"(da), "r"(db), "n"(scale_d));
#undef R_
}
template <int scale_d> __device__ __forceinline__ void wgmma4_n128(float* d, uint32_t da, uint32_t db) {
#define R_ "{%0,%1,%2,%3,%4,%5,%6,%7,%8,%9,%10,%11,%12,%13,%14,%15,%16,%17,%18,%19,%20,%21,%22,%23,%24,%25,%26,%27,%28,%29,%30,%31,%32,%33,%34,%35,%36,%37,%38,%39,%40,%41,%42,%43,%44,%45,%46,%47,%48,%49,%50,%51,%52,%53,%54,%55,%56,%57,%58,%59,%60,%61,%62,%63}"
  asm volatile("{\n.reg .pred p, q;\n.reg .b64 a, b;\nsetp.ne.b32 p, %66, 0;\nsetp.eq.b32 q, 0, 0;\nmov.b64 a, {%64, 0x40000040};\nmov.b64 b, {%65, 0x40000040};\n"
               "wgmma.mma_async.sync.aligned.m64n128k16.f32.bf16.bf16 " R_ ", a, b, p, 1, 1, 0, 1;\nadd.s64 a, a, 2;\nadd.s64 b, b, 128;\n"
               "wgmma.mma_async.sync.aligned.m64n128k16.f32.bf16.bf16 " R_ ", a, b, q, 1, 1, 0, 1;\nadd.s64 a, a, 2;\nadd.s64 b, b, 128;\n"
               "wgmma.mma_async.sync.aligned.m64n128k16.f32.bf16.bf16 " R_ ", a, b, q, 1, 1, 0, 1;\nadd.s64 a, a, 2;\nadd.s64 b, b, 128;\n"
               "wgmma.mma_async.sync.aligned.m64n128k16.f32.bf16.bf16 " R_ ", a, b, q, 1, 1, 0, 1;\n}\n"
               : "+f"(d[0]), "+f"(d[1]), "+f"(d[2]), "+f"(d[3]), "+f"(d[4]), "+f"(d[5]), "+f"(d[6]), "+f"(d[7]), "+f"(d[8]), "+f"(d[9]), "+f"(d[10]), "+f"(d[11]), "+f"(d[12]), "+f"(d[13]), "+f"(d[14]), "+f"(d[15]), "+f"(d[16]), "+f"(d[17]), "+f"(d[18]), "+f"(d[19]), "+f"(d[20]), "+f"(d[21]), "+f"(d[22]), "+f"(d[23]), "+f"(d[24]), "+f"(d[25]), "+f"(d[26]), "+f"(d[27]), "+f"(d[28]), "+f"(d[29]), "+f"(d[30]), "+f"(d[31]), "+f"(d[32]), "+f"(d[33]), "+f"(d[34]), "+f"(d[35]), "+f"(d[36]), "+f"(d[37]), "+f"(d[38]), "+f"(d[39]), "+f"(d[40]), "+f"(d[41]), "+f"(d[42]), "+f"(d[43]), "+f"(d[44]), "+f"(d[45]), "+f"(d[46]), "+f"(d[47]), "+f"(d[48]), "+f"(d[49]), "+f"(d[50]), "+f"(d[51]), "+f"(d[52]), "+f"(d[53]), "+f"(d[54]), "+f"(d[55]), "+f"(d[56]), "+f"(d[57]), "+f"(d[58]), "+f"(d[59]), "+f"(d[60]), "+f"(d[61]), "+f"(d[62]), "+f"(d[63])
               : "r"(da), "r"(db), "n"(scale_d));
#undef R_
}
template <int scale_d> __device__ __forceinline__ void wgmma_n32(float* d, uint64_t descA, uint64_t descB) {
  asm volatile("{\n.reg .pred p;\nsetp.ne.b32 p, %18, 0;\n"
               "wgmma.mma_async.sync.aligned.m64n32k16.f32.bf16.bf16 {%0,%1,%2,%3,%4,%5,%6,%7,%8,%9,%10,%11,%12,%13,%14,%15}, %16, %17, p, 1, 1, 0, 1;\n}\n"
               : "+f"(d[0]), "+f"(d[1]), "+f"(d[2]), "+f"(d[3]), "+f"(d[4]), "+f"(d[5]), "+f"(d[6]), "+f"(d[7]), "+f"(d[8]), "+f"(d[9]), "+f"(d[10]), "+f"(d[11]), "+f"(d[12]), "+f"(d[13]), "+f"(d[14]), "+f"(d[15])
               : "l"(descA), "l"(descB), "n"(scale_d));
}
template <int scale_d, int tnsp_a> __device__ __forceinline__ void wgmma_n40(float* d, uint64_t descA, uint64_t descB) {
  asm volatile("{\n.reg .pred p;\nsetp.ne.b32 p, %22, 0;\n"
               "wgmma.mma_async.sync.aligned.m64n40k16.f32.bf16.bf16 {%0,%1,%2,%3,%4,%5,%6,%7,%8,%9,%10,%11,%12,%13,%14,%15,%16,%17,%18,%19}, %20, %21, p, 1, 1, %23, 1;\n}\n"
               : "+f"(d[0]), "+f"(d[1]), "+f"(d[2]), "+f"(d[3]), "+f"(d[4]), "+f"(d[5]), "+f"(d[6]), "+f"(d[7]), "+f"(d[8]), "+f"(d[9]), "+f"(d[10]), "+f"(d[11]), "+f"(d[12]), "+f"(d[13]), "+f"(d[14]), "+f"(d[15]), "+f"(d[16]), "+f"(d[17]), "+f"(d[18]), "+f"(d[19])
               : "l"(descA), "l"(descB), "n"(scale_d), "n"(tnsp_a));
}
template <int scale_d> __device__ __forceinline__ void wgmma_n40_rs(float* d, const uint32_t* a, uint64_t descB) {
  asm volatile("{\n.reg .pred p;\nsetp.ne.b32 p, %25, 0;\n"
               "wgmma.mma_async.sync.aligned.m64n40k16.f32.bf16.bf16 {%0,%1,%2,%3,%4,%5,%6,%7,%8,%9,%10,%11,%12,%13,%14,%15,%16,%17,%18,%19}, {%20,%21,%22,%23}, %24, p, 1, 1, 1;\n}\n"
               : "+f"(d[0]), "+f"(d[1]), "+f"(d[2]), "+f"(d[3]), "+f"(d[4]), "+f"(d[5]), "+f"(d[6]), "+f"(d[7]), "+f"(d[8]), "+f"(d[9]), "+f"(d[10]), "+f"(d[11]), "+f"(d[12]), "+f"(d[13]), "+f"(d[14]), "+f"(d[15]), "+f"(d[16]), "+f"(d[17]), "+f"(d[18]), "+f"(d[19])
               : "r"(a[0]), "r"(a[1]), "r"(a[2]), "r"(a[3]), "l"(descB), "n"(scale_d));
}
__device__ __forceinline__ void wgmma_copy(float* d, uint32_t da, uint64_t descB) {
  asm volatile("{\n.reg .pred p;\n.reg .b64 a;\nsetp.ne.b32 p, 0, 0;\nmov.b64 a, {%64, 0x40000040};\n"
               "wgmma.mma_async.sync.aligned.m64n16k16.f32.bf16.bf16 {%0,%1,%2,%3,%4,%5,%6,%7}, a, %65, p, 1, 1, 0, 0;\nadd.s64 a, a, 2;\n"
               "wgmma.mma_async.sync.aligned.m64n16k16.f32.bf16.bf16 {%8,%9,%10,%11,%12,%13,%14,%15}, a, %65, p, 1, 1, 0, 0;\nadd.s64 a, a, 2;\n"
               "wgmma.mma_async.sync.aligned.m64n16k16.f32.bf16.bf16 {%16,%17,%18,%19,%20,%21,%22,%23}, a, %65, p, 1, 1, 0, 0;\nadd.s64 a, a, 2;\n"
               "wgmma.mma_async.sync.aligned.m64n16k16.f32.bf16.bf16 {%24,%25,%26,%27,%28,%29,%30,%31}, a, %65, p, 1, 1, 0, 0;\nadd.s64 a, a, 1018;\n"
               "wgmma.mma_async.sync.aligned.m64n16k16.f32.bf16.bf16 {%32,%33,%34,%35,%36,%37,%38,%39}, a, %65, p, 1, 1, 0, 0;\nadd.s64 a, a, 2;\n"
               "wgmma.mma_async.sync.aligned.m64n16k16.f32.bf16.bf16 {%40,%41,%42,%43,%44,%45,%46,%47}, a, %65, p, 1, 1, 0, 0;\nadd.s64 a, a, 2;\n"
               "wgmma.mma_async.sync.aligned.m64n16k16.f32.bf16.bf16 {%48,%49,%50,%51,%52,%53,%54,%55}, a, %65, p, 1, 1, 0, 0;\nadd.s64 a, a, 2;\n"
               "wgmma.mma_async.sync.aligned.m64n16k16.f32.bf16.bf16 {%56,%57,%58,%59,%60,%61,%62,%63}, a, %65, p, 1, 1, 0, 0;\n"
               "}\n"
               : "+f"(d[0]), "+f"(d[1]), "+f"(d[2]), "+f"(d[3]), "+f"(d[4]), "+f"(d[5]), "+f"(d[6]), "+f"(d[7]), "+f"(d[8]), "+f"(d[9]), "+f"(d[10]), "+f"(d[11]), "+f"(d[12]), "+f"(d[13]), "+f"(d[14]), "+f"(d[15]), "+f"(d[16]), "+f"(d[17]), "+f"(d[18]), "+f"(d[19]), "+f"(d[20]), "+f"(d[21]), "+f"(d[22]), "+f"(d[23]), "+f"(d[24]), "+f"(d[25]), "+f"(d[26]), "+f"(d[27]), "+f"(d[28]), "+f"(d[29]), "+f"(d[30]), "+f"(d[31]), "+f"(d[32]), "+f"(d[33]), "+f"(d[34]), "+f"(d[35]), "+f"(d[36]), "+f"(d[37]), "+f"(d[38]), "+f"(d[39]), "+f"(d[40]), "+f"(d[41]), "+f"(d[42]), "+f"(d[43]), "+f"(d[44]), "+f"(d[45]), "+f"(d[46]), "+f"(d[47]), "+f"(d[48]), "+f"(d[49]), "+f"(d[50]), "+f"(d[51]), "+f"(d[52]), "+f"(d[53]), "+f"(d[54]), "+f"(d[55]), "+f"(d[56]), "+f"(d[57]), "+f"(d[58]), "+f"(d[59]), "+f"(d[60]), "+f"(d[61]), "+f"(d[62]), "+f"(d[63])
               : "r"(da), "l"(descB));
}
template <int scale_d> __device__ __forceinline__ void wgmma_n192_rs(float* d, const uint32_t* a, uint32_t db) {
  asm volatile("{\n.reg .pred p;\n.reg .b64 b;\nsetp.ne.b32 p, %101, 0;\nmov.b64 b, {%100, 0x40000040};\n"
               "wgmma.mma_async.sync.aligned.m64n192k16.f32.bf16.bf16 {%0,%1,%2,%3,%4,%5,%6,%7,%8,%9,%10,%11,%12,%13,%14,%15,%16,%17,%18,%19,%20,%21,%22,%23,%24,%25,%26,%27,%28,%29,%30,%31,%32,%33,%34,%35,%36,%37,%38,%39,%40,%41,%42,%43,%44,%45,%46,%47,%48,%49,%50,%51,%52,%53,%54,%55,%56,%57,%58,%59,%60,%61,%62,%63,%64,%65,%66,%67,%68,%69,%70,%71,%72,%73,%74,%75,%76,%77,%78,%79,%80,%81,%82,%83,%84,%85,%86,%87,%88,%89,%90,%91,%92,%93,%94,%95}, {%96,%97,%98,%99}, b, p, 1, 1, 1;\n}\n"
               : "+f"(d[0]), "+f"(d[1]), "+f"(d[2]), "+f"(d[3]), "+f"(d[4]), "+f"(d[5]), "+f"(d[6]), "+f"(d[7]), "+f"(d[8]), "+f"(d[9]), "+f"(d[10]), "+f"(d[11]), "+f"(d[12]), "+f"(d[13]), "+f"(d[14]), "+f"(d[15]), "+f"(d[16]), "+f"(d[17]), "+f"(d[18]), "+f"(d[19]), "+f"(d[20]), "+f"(d[21]), "+f"(d[22]), "+f"(d[23]), "+f"(d[24]), "+f"(d[25]), "+f"(d[26]), "+f"(d[27]), "+f"(d[28]), "+f"(d[29]), "+f"(d[30]), "+f"(d[31]), "+f"(d[32]), "+f"(d[33]), "+f"(d[34]), "+f"(d[35]), "+f"(d[36]), "+f"(d[37]), "+f"(d[38]), "+f"(d[39]), "+f"(d[40]), "+f"(d[41]), "+f"(d[42]), "+f"(d[43]), "+f"(d[44]), "+f"(d[45]), "+f"(d[46]), "+f"(d[47]), "+f"(d[48]), "+f"(d[49]), "+f"(d[50]), "+f"(d[51]), "+f"(d[52]), "+f"(d[53]), "+f"(d[54]), "+f"(d[55]), "+f"(d[56]), "+f"(d[57]), "+f"(d[58]), "+f"(d[59]), "+f"(d[60]), "+f"(d[61]), "+f"(d[62]), "+f"(d[63]), "+f"(d[64]), "+f"(d[65]), "+f"(d[66]), "+f"(d[67]), "+f"(d[68]), "+f"(d[69]), "+f"(d[70]), "+f"(d[71]), "+f"(d[72]), "+f"(d[73]), "+f"(d[74]), "+f"(d[75]), "+f"(d[76]), "+f"(d[77]), "+f"(d[78]), "+f"(d[79]), "+f"(d[80]), "+f"(d[81]), "+f"(d[82]), "+f"(d[83]), "+f"(d[84]), "+f"(d[85]), "+f"(d[86]), "+f"(d[87]), "+f"(d[88]), "+f"(d[89]), "+f"(d[90]), "+f"(d[91]), "+f"(d[92]), "+f"(d[93]), "+f"(d[94]), "+f"(d[95])
               : "r"(a[0]), "r"(a[1]), "r"(a[2]), "r"(a[3]), "r"(db), "n"(scale_d));
}
__device__ __forceinline__ uint64_t make_desc(uint32_t addr, uint32_t lbo_bytes, uint32_t sbo_bytes) {
  return (uint64_t)((addr & 0x3FFFF) >> 4) | ((uint64_t)(lbo_bytes >> 4) << 16) | ((uint64_t)(sbo_bytes >> 4) << 32) | (1ull << 62);
}

__device__ __forceinline__ void ldsm_x4(uint32_t addr, uint32_t& r0, uint32_t& r1, uint32_t& r2, uint32_t& r3) {
  asm volatile("ldmatrix.sync.aligned.m8n8.x4.shared.b16 {%0,%1,%2,%3}, [%4];" : "=r"(r0), "=r"(r1), "=r"(r2), "=r"(r3) : "r"(addr) : "memory");
}
__device__ __forceinline__ void ldsm_x4_t(uint32_t addr, uint32_t& r0, uint32_t& r1, uint32_t& r2, uint32_t& r3) {
  asm volatile("ldmatrix.sync.aligned.m8n8.x4.trans.shared.b16 {%0,%1,%2,%3}, [%4];" : "=r"(r0), "=r"(r1), "=r"(r2), "=r"(r3) : "r"(addr) : "memory");
}
__device__ __forceinline__ void stsm_x4(uint32_t addr, uint32_t r0, uint32_t r1, uint32_t r2, uint32_t r3) {
  asm volatile("stmatrix.sync.aligned.m8n8.x4.shared.b16 [%0], {%1,%2,%3,%4};" :: "r"(addr), "r"(r0), "r"(r1), "r"(r2), "r"(r3) : "memory");
}
__device__ __forceinline__ void stsm_x4_t(uint32_t addr, uint32_t r0, uint32_t r1, uint32_t r2, uint32_t r3) {
  asm volatile("stmatrix.sync.aligned.m8n8.x4.trans.shared.b16 [%0], {%1,%2,%3,%4};" :: "r"(addr), "r"(r0), "r"(r1), "r"(r2), "r"(r3) : "memory");
}
__device__ __forceinline__ void sts128(uint32_t addr, uint32_t a, uint32_t b, uint32_t c, uint32_t d) {
  asm volatile("st.shared.v4.u32 [%0], {%1,%2,%3,%4};" :: "r"(addr), "r"(a), "r"(b), "r"(c), "r"(d) : "memory");
}
__device__ __forceinline__ float lds32f(uint32_t addr) {
  float v;
  asm volatile("ld.shared.f32 %0, [%1];" : "=f"(v) : "r"(addr) : "memory");
  return v;
}
__device__ __forceinline__ void sts32f(uint32_t addr, float a) {
  asm volatile("st.shared.f32 [%0], %1;" :: "r"(addr), "f"(a) : "memory");
}
__device__ __forceinline__ void mma_bf16(float (&c)[4], uint32_t a0, uint32_t a1, uint32_t a2, uint32_t a3, uint32_t b0, uint32_t b1) {
  asm volatile("mma.sync.aligned.m16n8k16.row.col.f32.bf16.bf16.f32 {%0,%1,%2,%3}, {%4,%5,%6,%7}, {%8,%9}, {%0,%1,%2,%3};"
               : "+f"(c[0]), "+f"(c[1]), "+f"(c[2]), "+f"(c[3]) : "r"(a0), "r"(a1), "r"(a2), "r"(a3), "r"(b0), "r"(b1));
}
__device__ __forceinline__ void mma_bf16_z(float (&c)[4], uint32_t a0, uint32_t a1, uint32_t a2, uint32_t a3, uint32_t b0, uint32_t b1) {
  asm volatile("mma.sync.aligned.m16n8k16.row.col.f32.bf16.bf16.f32 {%0,%1,%2,%3}, {%4,%5,%6,%7}, {%8,%9}, {%10,%10,%10,%10};"
               : "=f"(c[0]), "=f"(c[1]), "=f"(c[2]), "=f"(c[3]) : "r"(a0), "r"(a1), "r"(a2), "r"(a3), "r"(b0), "r"(b1), "f"(0.f));
}
__device__ __forceinline__ uint32_t movm_t(uint32_t v) {
  uint32_t r;
  asm volatile("movmatrix.sync.aligned.m8n8.trans.b16 %0, %1;" : "=r"(r) : "r"(v));
  return r;
}
__device__ __forceinline__ uint32_t pack_bf16(float lo, float hi) {
  uint32_t r;
  asm("cvt.rn.bf16x2.f32 %0, %1, %2;" : "=r"(r) : "f"(hi), "f"(lo));
  return r;
}
__device__ __forceinline__ float bf_lo(uint32_t v) { return __uint_as_float(v << 16); }
__device__ __forceinline__ float bf_hi(uint32_t v) { return __uint_as_float(v & 0xFFFF0000u); }
__device__ __forceinline__ void split3(float x, uint32_t& h, uint32_t& m, uint32_t& l) {
  h = pack_bf16(x, 0.f); x -= bf_lo(h);
  m = pack_bf16(x, 0.f); x -= bf_lo(m);
  l = pack_bf16(x, 0.f);
}
__device__ __forceinline__ float ex2(float x) { float r; asm("ex2.approx.ftz.f32 %0, %1;" : "=f"(r) : "f"(x)); return r; }
__device__ __forceinline__ float rcp_fast(float x) { float r; asm("rcp.approx.ftz.f32 %0, %1;" : "=f"(r) : "f"(x)); return r; }
__device__ __forceinline__ void red_v4(float* p, float a, float b, float c, float d) {
  asm volatile("red.global.add.v4.f32 [%0], {%1, %2, %3, %4};" :: "l"(p), "f"(a), "f"(b), "f"(c), "f"(d) : "memory");
}
__device__ __forceinline__ uint4 ld_ll(const uint4* p) {
  uint4 v;
  asm volatile("{\n.reg .b64 a, b;\nld.relaxed.gpu.global.v2.b64 {a, b}, [%4];\nmov.b64 {%0, %1}, a;\nmov.b64 {%2, %3}, b;\n}\n"
               : "=r"(v.x), "=r"(v.y), "=r"(v.z), "=r"(v.w) : "l"(p) : "memory");
  return v;
}
__device__ __forceinline__ void st_b64(uint2* p, uint32_t a, uint32_t b) {
  asm volatile("{\n.reg .b64 v;\nmov.b64 v, {%1, %2};\nst.relaxed.gpu.global.b64 [%0], v;\n}\n" :: "l"(p), "r"(a), "r"(b) : "memory");
}
__device__ __forceinline__ void st_b128(uint4* p, uint32_t a, uint32_t b, uint32_t c, uint32_t d) {
  asm volatile("{\n.reg .b128 v;\nmov.b128 v, {%1, %2, %3, %4};\nst.relaxed.gpu.global.b128 [%0], v;\n}\n" :: "l"(p), "r"(a), "r"(b), "r"(c), "r"(d) : "memory");
}
__device__ __forceinline__ uint4 ld_b128(const uint4* p) {
  uint4 v;
  asm volatile("{\n.reg .b128 v;\nld.relaxed.gpu.global.b128 v, [%4];\nmov.b128 {%0, %1, %2, %3}, v;\n}\n" : "=r"(v.x), "=r"(v.y), "=r"(v.z), "=r"(v.w) : "l"(p) : "memory");
  return v;
}

constexpr float LOG2E = 1.4426950408889634f;

struct Params {
  const __nv_bfloat16* wA_o;
  const __nv_bfloat16* wB_qkv;
  const __nv_bfloat16* wB_o;
  const unsigned* epoch;
  __nv_bfloat16* out;
};

#define ACC_DEF(d, n) _Pragma("unroll") for (int i_ = 0; i_ < (n); i_++) asm volatile("" : "=f"(d[i_]))
#define ACC_FENCE(d, n) _Pragma("unroll") for (int i_ = 0; i_ < (n); i_++) asm volatile("" : "+f"(d[i_]) :: "memory")
#define PIN(a, n) _Pragma("unroll") for (int i_ = 0; i_ < (n); i_++) asm volatile("" : "+f"((a)[i_]))
#define PINU(a, n) _Pragma("unroll") for (int i_ = 0; i_ < (n); i_++) asm volatile("" : "+r"((a)[i_]))

#define V_ADDR(p0, sw) uint32_t va_[2] = {(p0) + (srowoff >> 1) + (lhi ^ lsw2 ^ (sw)), (p0) + (srowoff >> 1) + ((32 + lhi) ^ lsw2 ^ (sw))}
#define STAGE_V(acc) { \
    _Pragma("unroll") for (int j_ = 0; j_ < 4; j_++) { \
      const float* a_ = (acc) + j_ * 8; \
      stsm_x4(va_[j_ & 1] + (j_ >> 1) * 8192, \
              pack_bf16(rs0 * a_[0], rs0 * a_[1]), pack_bf16(rs1 * a_[2], rs1 * a_[3]), pack_bf16(rs0 * a_[4], rs0 * a_[5]), pack_bf16(rs1 * a_[6], rs1 * a_[7])); } }
#define FRAG(dst, acc, TR, grp) { \
    _Pragma("unroll") for (int i_ = 15; i_ >= 0; i_--) { \
      const float r_ = (i_ & 8) ? rs1 : rs0; \
      const uint32_t w_ = pack_bf16(r_ * (acc)[4 * (i_ & 7) + (i_ >> 3) * 2], r_ * (acc)[4 * (i_ & 7) + (i_ >> 3) * 2 + 1]); \
      (dst)[8 + i_] = (TR) ? movm_t(w_) : w_; \
      if (i_ == 8 && warp >= 6 && mm < 15) { \
        _Pragma("unroll") for (int j_ = 0; j_ < 2; j_++) \
          st_b128(g_halo + (size_t)(mm * 8 + jj) * 512 + ((grp) * 4 + warp * 2 - 12 + j_) * 32 + lane, ((dst)[16 + j_ * 4] & ~1u) | H_BIT(l), (dst)[17 + j_ * 4], (dst)[18 + j_ * 4], (dst)[19 + j_ * 4]); } } \
    PINU((dst) + 8, 16); }
#define FRAG_PUT(src, slot) if (warp < 6) { _Pragma("unroll") for (int j_ = 0; j_ < 2; j_++) \
      sts128(sbase + OFF_S + (slot) * 8192 + 2048 + warp * 1024 + j_ * 512 + lane * 16, (src)[j_ * 4], (src)[j_ * 4 + 1], (src)[j_ * 4 + 2], (src)[j_ * 4 + 3]); }
#define FRAG_GET(dst, slot) { _Pragma("unroll") for (int j_ = 0; j_ < 2; j_++) \
      asm volatile("ld.shared.v4.u32 {%0, %1, %2, %3}, [%4];" : "=r"((dst)[j_ * 4]), "=r"((dst)[j_ * 4 + 1]), "=r"((dst)[j_ * 4 + 2]), "=r"((dst)[j_ * 4 + 3]) \
                   : "r"(sbase + OFF_S + (slot) * 8192 + warp * 1024 + j_ * 512 + lane * 16) : "memory"); }
#define RW(j) (((j) >> 1) * 4 + ((j) & 1))
template <int POS> __device__ __forceinline__ float exps16_(float* o, const float* p) {
  float s[4];
#pragma unroll
  for (int j = 0; j < 16; j++) { o[j] = ex2(POS ? p[RW(j)] : -p[RW(j)]); if (j < 4) s[j] = o[j]; else s[j & 3] += o[j]; }
  const float r = (s[0] + s[1]) + (s[2] + s[3]);
  return r + __shfl_xor_sync(0xffffffffu, r, 1);
}
template <int POS> __device__ __forceinline__ void exps16_fix(float* o, const float* p, float& sum) {
  if (__builtin_expect(__any_sync(0xffffffffu, !(sum > SUMLO && sum < SUMHI)), 0)) {
    float m = p[0], q[32];
#pragma unroll
    for (int j = 1; j < 16; j++) m = POS ? fmaxf(m, p[RW(j)]) : fminf(m, p[RW(j)]);
    const float x = __shfl_xor_sync(0xffffffffu, m, 1);
    m = POS ? fmaxf(m, x) : fminf(m, x);
#pragma unroll
    for (int j = 0; j < 16; j++) q[RW(j)] = p[RW(j)] - m;
    sum = exps16_<POS>(o, q);
  }
}
__device__ __forceinline__ void store16(const float* e, float sum, uint32_t dst, uint32_t dsw, int c0) {
  const float inv = rcp_fast(sum);
#pragma unroll
  for (int j = 0; j < 2; j++)
    sts128(dst + (((c0 + j) << 4) ^ dsw), pack_bf16(e[j * 8] * inv, e[j * 8 + 1] * inv), pack_bf16(e[j * 8 + 2] * inv, e[j * 8 + 3] * inv),
           pack_bf16(e[j * 8 + 4] * inv, e[j * 8 + 5] * inv), pack_bf16(e[j * 8 + 6] * inv, e[j * 8 + 7] * inv));
}
template <int POS> __device__ __forceinline__ void expp16(uint32_t* o, float* p) {
  {
#pragma unroll
    for (int r = 0; r < 4; r += 2) {
      float m = p[r];
#pragma unroll
      for (int j = 1; j < 8; j++) m = POS ? fmaxf(m, p[r + RW(j)]) : fminf(m, p[r + RW(j)]);
#pragma unroll
      for (int s = 1; s <= 2; s <<= 1) { const float x = __shfl_xor_sync(0xffffffffu, m, s); m = POS ? fmaxf(m, x) : fminf(m, x); }
#pragma unroll
      for (int j = 0; j < 8; j++) p[r + RW(j)] -= m;
    }
  }
#pragma unroll
  for (int j = 0; j < 8; j++) o[j] = pack_bf16(ex2(POS ? p[2 * j] : -p[2 * j]), ex2(POS ? p[2 * j + 1] : -p[2 * j + 1]));
}
__device__ __forceinline__ void scale32(float* o, const float* p, float c0, float c1) {
#pragma unroll
  for (int i = 0; i < 32; i++) asm volatile("mul.f32 %0, %1, %2;" : "=f"(o[i]) : "f"(p[i]), "f"((i & 2) ? c1 : c0));
}
__device__ __forceinline__ bool any_big(const float* p) {
  float m[4];
#pragma unroll
  for (int i = 0; i < 32; i++) m[i >> 3] = (i & 7) ? fmaf(p[i], p[i], m[i >> 3]) : p[i] * p[i];
  return __any_sync(0xffffffffu, !(fmaxf(fmaxf(m[0], m[1]), fmaxf(m[2], m[3])) < BIGLIM));
}
__device__ __forceinline__ void phiq_a(float* p, bool big) {
  if (__builtin_expect(!big, 1)) {
#pragma unroll
    for (int j = 0; j < 16; j++) p[j] = ex2(p[j]);
  }
}
template <int NEXT> __device__ __forceinline__ void phiq_b(uint32_t* o, float* p, bool big) {
  if (__builtin_expect(big, 0)) {
    expp16<0>(o, p); expp16<1>(o + 8, p);
  } else {
    if (NEXT) phiq_a(p + 16, false);
#pragma unroll
    for (int j = 0; j < 4; j++) {
      const float a = p[4 * j], b = p[4 * j + 1], c = p[4 * j + 2], d = p[4 * j + 3];
      const float ab = a * b, cd = c * d, r = rcp_fast(ab * cd), x = r * cd, y = r * ab;
      o[2 * j] = pack_bf16(x * b, x * a); o[2 * j + 1] = pack_bf16(y * d, y * c);
      o[8 + 2 * j] = pack_bf16(a, b); o[9 + 2 * j] = pack_bf16(c, d);
    }
  }
}
#define SCHED_FENCE() asm volatile("pmevent 0;" ::: "memory")

__global__ void __cluster_dims__(2, 1, 1) __launch_bounds__(384, 1)
mega_kernel(const Params prm  , const __grid_constant__ CUtensorMap tm_x0, const __grid_constant__ CUtensorMap tm_os,
            const __grid_constant__ CUtensorMap tm_o, const __grid_constant__ CUtensorMap tm_wf,
            const __grid_constant__ CUtensorMap tm_wqA, const __grid_constant__ CUtensorMap tm_wqB,
            const __grid_constant__ CUtensorMap tm_woA, const __grid_constant__ CUtensorMap tm_woB,
            const __grid_constant__ CUtensorMap tm_phi) {
  extern __shared__ __align__(1024) uint8_t smem_raw[];
  const uint32_t sbase = smem_u32(smem_raw);
  const uint32_t bar_full = sbase + OFF_BAR;
  const uint32_t bar_done = bar_full + 384;
  const uint32_t bar_stat = bar_full + 768, bar_stat2 = bar_full + 776, bar_epi = bar_full + 784, bar_phi = bar_full + 936  , bar_halo = bar_full + 904  ;
  const uint32_t bar_xr = bar_full + 800, bar_lx = bar_full + 808, bar_stg = bar_full + 832;
  const uint32_t bar_chk = bar_full + 848;

  const int warp = __shfl_sync(0xffffffffu, threadIdx.x >> 5, 0), lane = threadIdx.x & 31;
  const uint32_t bar_kx = sbase + OFF_ID + 384 + warp * 8;
  uint32_t rank;
  asm volatile("mov.u32 %0, %%cluster_ctarank;" : "=r"(rank));
  const int aux = (int)blockIdx.x - NMAIN, tp = (int)(blockIdx.x >> 1) - 4;
  const int gp = tp < 0 ? 0 : (tp < 32 ? tp & 7 : 1 + (tp - 32) % 7), me = tp < 0 ? tp + 8 : (tp < 32 ? tp >> 3 : 4 + (tp - 32) / 7);
  const int jj = me, cc = gp;
  const int cta = aux >= 0 ? -1 : (cc * 8 + jj) * 2 + (int)rank;
  const int mm = cc * 2 + (int)rank;

#define LOAD_EPOCH() const unsigned epoch = ld_relaxed(prm.epoch), ep1 = epoch + 1; (void)epoch
  int budget = 1 << 22;
  unsigned epoch0 = 0;

  if (cta >= 0) {
    if (warp >= 8 && warp < 10 && elect_one()) {
      const int u = warp - 8;
      const uint32_t fb = bar_full + u * 8;
      mbar_init(fb, 1);
      asm volatile("fence.mbarrier_init.release.cluster;" ::: "memory");
      fence_proxy_async_smem();
      mbar_expect_tx(fb, QST + SLOT);
      if (STAG2 && u) __nanosleep(STAG2);
      tma_load_t(sbase + OFF_RA + u * SLOT, &tm_x0, fb, srcb(jj, u) * 128, mm * 128);
#pragma unroll
      for (int i = 0; i < 6; i++) tma_load_2d(sbase + u * QST + i * 4096, &tm_wqA, fb, jj * 128 + (i >> 1) * 1024, srcb(jj, u) * 128 + (i & 1) * 32);
      PROFT(472 + u);
    }
    __syncwarp();
    if (elect_one()) {
#pragma unroll
      for (int i = 0; i < 4; i++) {
        const int u = warp * 4 + i;
        mbar_init(u < 2 ? bar_kx : bar_full + u * 8, ((u >= 4 && u < 11) || (u > 32 && u != 40)) ? 2 : 1); mbar_init(bar_done + u * 8, 16);
      }
      mbar_init(bar_stat + warp * 16, 0x111111181182ull >> (4 * warp) & 15);
      mbar_init(bar_stat + warp * 16 + 8, 0x111111121811ull >> (4 * warp) & 15);
      mbar_init(bar_chk + 112 + (warp & 7) * 8, 1);
      mbar_init(bar_kx, 1);
      asm volatile("fence.mbarrier_init.release.cluster;" ::: "memory");
    }
    __syncwarp();
    if (threadIdx.x == 383) epoch0 = ld_relaxed(prm.epoch);
    if (PRL == 0 && lane == 0 && warp >= 8) PROFT(440 + warp - 8);
    __syncthreads();
    if (PRL == 0 && threadIdx.x == 256) PROFT(444);
    asm volatile("barrier.cluster.arrive.relaxed.aligned;" ::: "memory");
  }

  if (cta < 0) {
    LOAD_EPOCH();
    const uint32_t buf = sbase + warp * SLOT, bar = sbase + OFF_BAR + warp * 16;
    const uint32_t lsw = (lane & 7) << 4, lhi = (lane >> 4) << 4, lrow = (lane & 15) * 128;
    const bool el = elect_one();
    if (el) {
      mbar_init(bar, 1); mbar_init(bar + 8, 1);
      asm volatile("fence.mbarrier_init.release.cluster;" ::: "memory");
    }
#pragma unroll 1
    for (int rd = 0; rd < (NLAYERS > 1 ? 5 : 2); rd++) {
      if (rd >= 2 && warp >= 8) break;
      const int tk = rd < 2 ? aux * 12 + warp : aux * 8 + warp;
      const int half = tk & 1;
      const int blk = rd < 2 ? (tk >> 1) * 2 + rd : (4 - rd) * 16 + (tk >> 1);
      const CUtensorMap* tm = rd < 2 ? &tm_wqA : (rd == 2 ? &tm_wqB : &tm_wf);
      const int j0 = (blk & 15) >> 1;
#define AUX_LOAD(n) { const uint32_t d_ = buf + ((n) & 1) * 8192, b_ = bar + ((n) & 1) * 8; const int r_ = kslice(j0, 2 * ((AUXORD >> (4 * (n))) & 7) + half) * 64; \
        mbar_expect_tx(b_, 8192); tma_load_2d(d_, tm, b_, blk * 64, r_); tma_load_2d(d_ + 4096, tm, b_, blk * 64, r_ + 32); }
      if (el) {
        if (rd == 3) { wait_flag(&g_flags.wfready[j0].v, ep1 * 16); fence_proxy_async_global(); }
        AUX_LOAD(0); AUX_LOAD(1);
      }
      __syncwarp();
      float cs[8][4];
#pragma unroll
      for (int i = 0; i < 8; i++) cs[i][0] = cs[i][1] = cs[i][2] = cs[i][3] = 0.f;
#pragma unroll 1
      for (int n = 0; n < 8; n++) {
        const uint32_t tb = buf + (n & 1) * 8192 + lrow;
        mbar_wait(bar + (n & 1) * 8, (n >> 1) & 1);
#pragma unroll
        for (int i = 0; i < 16; i++) {
          uint32_t b0, b1, b2, b3;
          ldsm_x4_t(tb + (i >> 2) * 2048 + (((i & 3) * 32 + lhi) ^ lsw), b0, b1, b2, b3);
          mma_bf16(cs[2 * (i & 3)], 0x3F803F80u, 0x3F803F80u, 0x3F803F80u, 0x3F803F80u, b0, b1);
          mma_bf16(cs[2 * (i & 3) + 1], 0x3F803F80u, 0x3F803F80u, 0x3F803F80u, 0x3F803F80u, b2, b3);
        }
        __syncwarp();
        if (el && n < 6) AUX_LOAD(n + 2);
        __syncwarp();
      }
      if (lane < 4) {
#pragma unroll
        for (int i = 0; i < 8; i++) st_b64(&g_colsum[rd >= 2][blk * 32 + i * 4 + lane][half], __float_as_uint(cs[i][0]), (__float_as_uint(cs[i][1]) & ~3u) | (ep1 & 3));
      }
      __syncwarp();
    }
  } else if (warp >= 8) {
    asm volatile("setmaxnreg.dec.sync.aligned.u32 40;");
    if (warp == 8) {
      const bool el = elect_one();
      cluster_wait();
      if (el) {
        if (PRL == 0) PROFT(445);
#pragma unroll 1
        for (int l = 0; l < NLAYERS; l++) {
          const uint32_t par = l & 1;
          const CUtensorMap* tqk = par ? &tm_wf : &tm_wqA;
          const CUtensorMap* tv = par ? &tm_wqB : &tm_wqA;
          const CUtensorMap* two = par ? &tm_woB : &tm_woA;
          if (l == 1) { LOAD_EPOCH(); wait_flag(&g_flags.wfready[jj].v, ep1 * 16); fence_proxy_async_global(); }
#pragma unroll 1
          for (int u = l ? 0 : EARLY; u < 32; u++) {
            if (u >= 4) mbar_wait_sl(bar_done + (u - 4) * 8, par);
            else mbar_wait_sl(bar_done + (43 + u + (u >> 1)) * 8, par ^ 1);
            const uint32_t fb = bar_full + u * 8;
            const int v = (l || u > 7) ? u : u - 4;
            const bool res = u < 11 || (u >= 18 && u < 22);
            mbar_expect_tx(fb, res ? QST : QST + SLOT);
            const int row = kslice(jj, v < 4 ? v & 1 : (u < 18 ? u - 2 : (u < 22 ? u - 6 : u - 20))) * 64 + (int)rank * 32;
            const int ps = v < 4 ? v >> 1 : (u >= 18), col = jj * 128 + ps * 64;
            const int c0 = par ? jj * 128 + (ps ? 0 : 1024) : col;
            const uint32_t dst = sbase + (u & 3) * QST + rank * 4096;
            tma_load_2d_mc(dst, tqk, fb, c0, row);
            tma_load_2d_mc(dst + 8192, tqk, fb, c0 + (par ? 64 : 1024), row);
            tma_load_2d_mc(dst + 16384, tv, fb, col + 2048, row);
            if (u < 8) PROFL3(472 + u);
          }
#pragma unroll 1
          for (int s = 0; s < 16; s++) {
            if (s < 5) { if (s != 2 && s != 4) mbar_wait_sl(bar_done + (28 + s) * 8, par); }
            else if (s != 14) mbar_wait_sl(bar_done + (27 + s - (s == 15)) * 8, par);
            const uint32_t fb = bar_full + (32 + s) * 8;
            mbar_expect_tx(fb, SLOT);
            tma_load_2d_mc(sbase + rank * 8192 + (uint32_t)((WO_BSLOT >> (4 * s)) & 15) * SLOT, two, fb, jj * 128 + (int)rank * 64, wslice(jj, s) * 64);
            const int ts = s + 1;
            if (s >= 5 && ts < 8) {
              mbar_expect_tx(bar_chk - 8 + ts * 8, SLOT);
              tma_load_t(sbase + (uint32_t)((WO_ASLOT(par) >> (4 * ts)) & 15) * SLOT, &tm_o, bar_chk - 8 + ts * 8, wslice(jj, ts) * 64, mm * 128);
            }
          }
        }
      }
      __syncwarp();
    } else if (warp == 9) {
      const bool el = elect_one();
      if (el) {
#pragma unroll
        for (int i = 0; i < 2; i++) {
          mbar_expect_tx(bar_full + 32 + i * 8, SLOT);
          mbar_wait_sl(bar_full + (i ? OWNW1 : OWNW0) * 8, 0);
          tma_load_t(sbase + OFF_S + i * SLOT, &tm_x0, bar_full + 32 + i * 8, jj * 128 + i * 64, mm * 128);
        }
      }
      __syncwarp();
      LOAD_EPOCH();
#pragma unroll 1
      for (int lp = 0; lp < 4 * NLAYERS; lp++) {
        const int l = lp >> 2, ph = lp & 3;
        if (ph == 3) continue;
        const uint32_t par = l & 1;
        const unsigned* pp = reinterpret_cast<const unsigned*>(g_obuf + (ph >> 1) * 64 + (size_t)(mm * 128 + (ph ? 0 : S_LEN) + ((lane & 7) | PROWS) * 16 + (jj & 1) * 8) * D_MODEL +
                                                               (jj >> 1) * 16 + srcb(jj, lane >> 3) * 128);
        const CUtensorMap* tm = lp ? &tm_o : &tm_x0;
        const int row = mm * 128 + ((ph || !l) ? 0 : S_LEN);
        const uint32_t bit = ph ? O_BIT(l) : X_BIT(l - 1);
        const uint32_t slots = ph ? (uint32_t)(WO_ASLOT(par) >> (ph * 32 - 28)) : 0x8769876u;
        const unsigned long long fr = ph == 0 ? XPACE : ph == 1 ? (par ? FRB : 0x35351F1E1Dull) : 0x27262524232232ull;
        uint32_t no = (lp == 0 || (lp & 7) == 1) ? 0 : (ph == 1 ? NOB : (ph ? NO1 : NOX)), v0 = 0, v1 = 0;
        mbar_wait_sl(ph ? bar_done + ((uint32_t)fr & 63) * 8 : (l ? bar_done + 47 * 8 : bar_full), ph ? par : (l ? par ^ 1 : 0));
        if (el && ph) PROFT(324 + l * 16 + ph);
        __syncwarp();
        if (no && (ph == 1 ? SPD1 : (ph ? SPD2 : SPD0))) __nanosleep(ph == 1 ? SPD1 : (ph ? SPD2 : SPD0));
        if (no) { v0 = ld_relaxed(pp); if (ph != 1) __nanosleep(POLLGAP); v1 = ld_relaxed(pp); }
#pragma unroll 1
        for (int i = lp ? 0 : 4; i < (ph == 1 ? 5 : 7); i++, no >>= 8) {
          uint32_t op[4] = {(lp ? bar_chk + (ph >> 1) * 112 : bar_full + 32) + i * 8  , sbase + ((slots >> (4 * i)) & 15) * SLOT,
                            (uint32_t)(srcb(jj, i) * 128 + (ph >> 1) * 64), bar_done + ((uint32_t)(fr >> (8 * i)) & 63) * 8};
          PINU(op, 4);
          if (el) mbar_expect_tx(op[0], SLOT);
#pragma unroll 1
          for (int it = 0; (no & 0xFF) && it < (1 << 18); it++) {
            no &= __ballot_sync(0xffffffffu, (v0 ^ bit) & 1) >> (8 * i);
            if (no) v0 = ld_relaxed(pp);
            if (!(no & 0xFF)) break;
            no &= __ballot_sync(0xffffffffu, (v1 ^ bit) & 1) >> (8 * i);
            if (no) v1 = ld_relaxed(pp);
          }
          if (i >= (ph ? 1 : 4)) mbar_wait_sl(op[3], par);
          if (el) {
            if (i == 0) PROFT(320 + l * 16 + ph);
            PROFL3(448 + ph * 8 + i);
            tma_load_t(op[1], tm, op[0], op[2], row);
          }
          __syncwarp();
        }
        if (ph == 0 && el) {
          if (l) { wait_flag(&g_flags.xready[l][mm].v, ep1 * 8); fence_proxy_async_global(); }
#pragma unroll 1
          for (int u = 11; u < 34; u++) {
            if (u == 18) u = 22;
            mbar_wait_sl(bar_done + (u - 4) * 8, par);
            if (u == 32) mbar_expect_tx(bar_xr, 2 * SLOT);
            tma_load_t(sbase + OFF_RA + (u & 3) * SLOT, tm, u < 32 ? bar_full + u * 8 : bar_xr, kslice(jj, u < 18 ? u - 2 : (u < 32 ? u - 20 : u - 32)) * 64, row);
          }
        }
        __syncwarp();
      }
      if (el && atomicAdd(&g_flags.done.v, 1) == ep1 * NMAIN - 1) asm volatile("st.relaxed.gpu.global.u32 [%0], %1;" :: "l"(&g_flags.epoch.v), "r"(ep1) : "memory");
      __syncwarp();
      cluster_wait();
    } else {
      const int hw = warp - 10;
      if (elect_one()) {
        const uint32_t fb = bar_full + 16 + hw * 8;
        mbar_expect_tx(fb, QST + SLOT);
#pragma unroll
        for (int i = 0; i < 6; i++) tma_load_2d(sbase + (2 + hw) * QST + i * 4096, &tm_wqA, fb, jj * 128 + (i >> 1) * 1024, srcb(jj, 2 + hw) * 128 + (i & 1) * 32);
        tma_load_t(sbase + OFF_RA + (2 + hw) * SLOT, &tm_x0, fb, srcb(jj, 2 + hw) * 128, mm * 128);
        mbar_arrive_local(fb + 32);
        if (PRL == 0) PROFT(446 + hw);
      }
      __syncwarp();
      const unsigned epoch = hw ? __shfl_sync(0xffffffffu, epoch0, 31) : ld_relaxed(prm.epoch), ep1 = epoch + 1;
      const bool el = elect_one();
      cluster_wait();
      if (hw == 0) {
        mbar_wait_sl(bar_full + 8, 0);
        if (lane < 7) prefetch_tmap(lane == 0 ? &tm_os : lane == 1 ? &tm_o : lane == 2 ? &tm_wf : lane == 3 ? &tm_wqB : lane == 4 ? &tm_woA : lane == 5 ? &tm_woB : &tm_phi);
#pragma unroll 1
        for (int i = 0; i < (NLAYERS > 1 ? 5 : 0); i++) {
          if (i == 0) mbar_wait_sl(bar_done + FD0 * 8, 0);
          if (el) {
            if (i == 0) { mbar_expect_tx(bar_phi, 2 * SLOT + 8192); tma_load_2d(sbase + OFF_PHI, &tm_phi, bar_phi, 0, jj * 128); }
            else tma_load_2d(sbase + 12 * SLOT - 4096 + i * 4096, &tm_wqB, bar_phi, jj * 128 + ((i - 1) >> 1) * 64, mm * 64 + (~i & 1) * 32);
          }
          __syncwarp();
          __nanosleep(PFGAP);
        }
      } else {
        if (lane < 24) {
          const uint32_t one = (lane & 8) ? 0u : 0x3F80u << ((lane & 1) * 16), w = (lane >> 1) & 3;
          sts128(sbase + OFF_ID + lane * 16, w == 0 ? one : 0u, w == 1 ? one : 0u, w == 2 ? one : 0u, w == 3 ? one : 0u);
        }
#pragma unroll 1
        for (int b = 0; b < 2; b++) {
          float4* z = reinterpret_cast<float4*>(g_kv[b] + (jj * 4) * KVH + mm * (4 * KVH / 16)) + lane;
#pragma unroll
          for (int i = 0; i < 6; i++) z[i * 32] = make_float4(0.f, 0.f, 0.f, 0.f);
        }
#pragma unroll 1
        for (int i = 0; i < 16; i++) {
          const int b = i >> 2;
          const uint32_t v = (b == 0 ? O_BIT(0) : b == 1 ? X_BIT(0) : H_BIT(0)) + 1;
          uint4* p = b < 2 ? reinterpret_cast<uint4*>(g_obuf + (size_t)(b * S_LEN + mm * 128 + (i & 3) * 32 + (lane >> 3) * 8) * D_MODEL + jj * 128 + (b ? 0 : 64)) + (lane & 7)
                           : g_halo + (size_t)(mm * 8 + jj) * 512 + i * 32 + lane;
          *p = make_uint4(v, v, v, v);
        }
        fence_proxy_async_global();
      }
      __syncwarp();
      uint32_t chkp = 0;
#pragma unroll 1
      for (int lp = 0; lp < 8 * NLAYERS; lp++) {
        const int l = lp >> 3, tk = lp & 7, ph = tk ? 2 - hw : 0;
        const uint32_t par = l & 1;
        int lane; asm volatile("mov.u32 %0, %%laneid;" : "=r"(lane));
        if (tk == 5 || (hw && tk == 0 && l)) {
          const uint32_t bit = ph ? O_BIT(l) : X_BIT(l - 1);
          uint32_t slots = ph ? (uint32_t)(WO_ASLOT(par) >> (ph * 32 - 28)) : 0x8769876u;
          const uint32_t a0 = sbase + (lane & 7) * 126 + lane * 4 + (lane & 1) * 14;
#pragma unroll 1
          for (int c = 0; c < 7; c++, slots >>= 4) {
            const uint32_t cb = bar_chk + 112 - hw * 112 + c * 8;
#pragma unroll 1
            for (int it = 0; it < (1 << 12); it++) {
              mbar_wait_sl(cb, (chkp >> c) & 1);
              chkp ^= 1u << c;
              if (el) PROFL3(384 + ph * 8 + c);
              uint32_t bad;
              asm volatile("{\n.reg .b32 w<16>;\n"
                           "ld.shared.u32 w0, [%1 + 0];\n"
                           "ld.shared.u32 w1, [%1 + 1024];\n"
                           "ld.shared.u32 w2, [%1 + 2048];\n"
                           "ld.shared.u32 w3, [%1 + 3072];\n"
                           "ld.shared.u32 w4, [%1 + 4096];\n"
                           "ld.shared.u32 w5, [%1 + 5120];\n"
                           "ld.shared.u32 w6, [%1 + 6144];\n"
                           "ld.shared.u32 w7, [%1 + 7168];\n"
                           "ld.shared.u32 w8, [%1 + 8192];\n"
                           "ld.shared.u32 w9, [%1 + 9216];\n"
                           "ld.shared.u32 w10, [%1 + 10240];\n"
                           "ld.shared.u32 w11, [%1 + 11264];\n"
                           "ld.shared.u32 w12, [%1 + 12288];\n"
                           "ld.shared.u32 w13, [%1 + 13312];\n"
                           "ld.shared.u32 w14, [%1 + 14336];\n"
                           "ld.shared.u32 w15, [%1 + 15360];\n"
                           "lop3.b32 w0, w0, w1, %2, 0x7E;\n"
                           "lop3.b32 w2, w2, w3, %2, 0x7E;\n"
                           "lop3.b32 w4, w4, w5, %2, 0x7E;\n"
                           "lop3.b32 w6, w6, w7, %2, 0x7E;\n"
                           "lop3.b32 w8, w8, w9, %2, 0x7E;\n"
                           "lop3.b32 w10, w10, w11, %2, 0x7E;\n"
                           "lop3.b32 w12, w12, w13, %2, 0x7E;\n"
                           "lop3.b32 w14, w14, w15, %2, 0x7E;\n"
                           "lop3.b32 w0, w0, w2, w4, 0xFE;\nlop3.b32 w6, w6, w8, w10, 0xFE;\nlop3.b32 w0, w0, w12, w14, 0xFE;\nlop3.b32 %0, w0, w6, 1, 0xA8;\n}\n"
                           : "=r"(bad) : "r"(a0 + (slots & 15) * SLOT), "r"(bit) : "memory");
              if (__all_sync(0xffffffffu, bad == 0)) break;
              if (el) {
                fence_proxy_async_smem();
                mbar_expect_tx(cb, SLOT);
                tma_load_t(sbase + (slots & 15) * SLOT, &tm_o, cb, srcb(jj, c) * 128 + (ph >> 1) * 64, mm * 128 + (ph ? 0 : S_LEN));
                RETRY_COUNT();
              }
              __syncwarp();
            }
            if (el) { mbar_arrive_local(bar_full + (c + (ph ? 25 + ph * 8 : 4)) * 8); PROFL3(416 + ph * 8 + c); }
            __syncwarp();
          }
        } else if (hw && (tk & 5) == 1) {
          {
            const int hp = tk >> 1;
            const uint4* src = reinterpret_cast<const uint4*>(g_colsum[par][jj * 64 + hp * 32 + lane]);
            uint32_t bad;
            int it = 0;
            float c[6];
            do {
              bad = 0;
#pragma unroll
              for (int p = 0; p < 3; p++) {
                const uint4 v = ld_ll(src + ((par && p < 2) ? (hp ? -32 : 512) + p * 32 : p * 512));
                bad |= (v.y ^ ep1) | (v.w ^ ep1);
                c[2 * p] = __uint_as_float(v.x) + __uint_as_float(v.z); c[2 * p + 1] = __uint_as_float(v.y) + __uint_as_float(v.w);
              }
              bad &= 3;
              if (bad) __nanosleep(CSGAP);
            } while (bad && ++it < (1 << 16));
#pragma unroll
            for (int p = 0; p < 6; p++) {
              uint32_t h, m, lo;
              split3(c[p], h, m, lo);
              sts128(sbase + OFF_LNB + hp * 4096 + (p >> 1) * 1024 + lane * 32 + (p & 1) * 16, h | (m << 16), h | (lo << 16), h | (m << 16), lo | (m << 16));
            }
            fence_proxy_async_smem();
            __syncwarp();
            if (el) { mbar_arrive_local(hp ? bar_stat2 : bar_stat); if (hp == 0) PROFT(324 + l * 16); }
            __syncwarp();
          }
        } else if (tk == 0) {
          mbar_wait_sl(bar_done + (l ? 24 : 56), par);
          const uint4* sp = reinterpret_cast<const uint4*>(g_stats + (size_t)(mm * 128) * 8) + lane;
          if (el) PROFL3(484);
#pragma unroll 1
          for (int hf = 2 * hw; hf < (l ? 4 : 2 + 2 * hw); hf++) {
            if (NLAYERS > 1 && l == 0 && el) tma_load_2d(sbase + 11 * SLOT + hf * 4096, &tm_wqB, bar_phi, 1024 + jj * 128 + (hf >> 1) * 64, mm * 64 + (hf & 1) * 32);
            __syncwarp();
            uint4 v[4];
            uint32_t bad;
            int it = 0;
            do {
              bad = 0;
#pragma unroll
              for (int i = 0; i < 4; i++) { v[i] = ld_ll(sp + (hf * 4 + i) * 32); bad |= (v[i].y ^ STAT_TAG(l)) | (v[i].w ^ STAT_TAG(l)); }
              bad &= 3;
              if (bad) __nanosleep(200);
            } while (bad && ++it < (1 << 16));
            __syncwarp();
            if (el) PROFL3(480 + hf);
            float mean = 0.f, m2 = 0.f;
#pragma unroll
            for (int i = 0; i < 4; i++) {
              float a = __uint_as_float(v[i].x) + __uint_as_float(v[i].z);
              a += __shfl_xor_sync(0xffffffffu, a, 1); a += __shfl_xor_sync(0xffffffffu, a, 2);
              a *= 0.125f;
              const float e0 = __uint_as_float(v[i].x) - a, e1 = __uint_as_float(v[i].z) - a;
              float q = fmaf(fmaf(e0, e0, e1 * e1), 128.f, __uint_as_float(v[i].y) + __uint_as_float(v[i].w));
              q += __shfl_xor_sync(0xffffffffu, q, 1); q += __shfl_xor_sync(0xffffffffu, q, 2);
              if ((lane & 3) == i) { mean = a; m2 = q; }
            }
            const uint32_t row = hf * 32 + (lane & 3) * 8 + (lane >> 2);
            uint32_t h, m, lo;
            split3(-0.5f * mean, h, m, lo);
            sts128(sbase + OFF_LNA + row * 16, h | (h << 16), m | (h << 16), lo | (m << 16), m | (lo << 16));
            sts32f(sbase + OFF_ST + row * 4, rsqrtf(m2 * (1.f / 1024.f) + 1e-5f));
          }
          if (hw) continue;
          fence_proxy_async_smem();
          __syncwarp();
          if (el) { mbar_arrive_local(bar_stat); PROFT(323 + l * 16); }
          __syncwarp();
#pragma unroll 1
          for (int i = 0; i < 8 - 4 * l; i++) {
            asm volatile("prefetch.global.L2 [%0];" :: "l"(i < 4 ? (l ? prm.wB_o : prm.wA_o) + (size_t)cta * 8192 + i * 2048 + lane * 64
                                                                 : prm.wB_qkv + (size_t)(cta * 8 + (i - 4) * 2 + (lane >> 4)) * 3072 + 2048 + (lane & 15) * 64));
            __nanosleep(PFGAP);
          }
        } else if (lp == 3) {
#pragma unroll 1
          for (int c = 0; c < (NLAYERS > 1 ? 8 : 0); c++) {
            if (!(c & 3)) { asm volatile("bar.sync %0, 288;" :: "r"(BAR_WF + (c >> 2)) : "memory"); fence_proxy_async_smem(); }
            if (el) {
              tma_store_2d(&tm_wf, sbase + 11 * SLOT + c * 4096, (c < 4 ? 1024 : -128) + jj * 128 + (c >> 1) * 64, mm * 64 + (c & 1) * 32);
              if (c == 7) {
                asm volatile("cp.async.bulk.commit_group;\ncp.async.bulk.wait_group.read 0;" ::: "memory");
                mbar_arrive_local(bar_phi + 8);
              } else __nanosleep(WFGAP);
            }
            __syncwarp();
          }
          if (el) { bulk_commit_wait(); signal_release(&g_flags.wfready[jj].v); PROFT(335); }
          __syncwarp();
        } else if (tk == 2 || tk == 4) {
          if (par) continue;
          const int i = tk >> 2;
          mbar_wait_sl(bar_done + (i ? HW1 : (hw ? 19 : HW0)) * 8, 0);
          const uint4* src = g_halo + (size_t)(mm * 8 + jj - 8) * 512 + i * 256 + hw * 128 + lane;
          uint4 v[4];
          int it = 0;
          bool ok;
          do {
#pragma unroll
            for (int j = 0; j < 4; j++) v[j] = mm ? ld_b128(src + j * 32) : make_uint4(H_BIT(l), 0, 0, 0);
            ok = __all_sync(0xffffffffu, (((v[0].x ^ H_BIT(l)) | (v[1].x ^ H_BIT(l)) | (v[2].x ^ H_BIT(l)) | (v[3].x ^ H_BIT(l))) & 1) == 0);
          } while (!ok && ++it < (1 << 16));
#pragma unroll
          for (int j = 0; j < 4; j++) sts128(sbase + OFF_S + hw * 8192 + j * 512 + lane * 16, v[j].x, v[j].y, v[j].z, v[j].w);
          __syncwarp();
          if (el) { mbar_arrive_local(bar_halo + hw * 8); PROFT(331 + l * 16 + i * 2 + hw); }
          __syncwarp();
        } else if (tk == 6 && hw == 0 && l < NLAYERS - 1) {
          bar_sync<BAR_X1, 288>();
          if (el) {
            PROFT(328 + l * 16);
            mbar_wait_sl(bar_full + XD * 8, par ^ 1);
            tma_store_t(&tm_o, sbase + 11 * SLOT, jj * 128 + 64, mm * 128 + S_LEN);
            bulk_commit_wait();
            signal_release(&g_flags.xready[l + 1][mm].v);
            PROFT(330 + l * 16);
          }
          __syncwarp();
        }
      }
    }
    cluster_sync();
  } else {
    asm volatile("setmaxnreg.inc.sync.aligned.u32 232;");
    const int wg = warp >> 2;
    const int r0 = warp * 16;
    const uint32_t pK = sbase + OFF_S, pV = sbase + OFF_S + SLOT;
#define PMASKS(on, bit) const uint32_t pm0 = ((on) && t == (g >> 1)), pbit = (bit)
#define PBIT(w) (((w) & ~pm0) | (pbit & pm0))
#define LANE_CONSTS() \
    int lane; asm volatile("mov.u32 %0, %%laneid;" : "=r"(lane)); \
    const int g = lane >> 2, t = lane & 3; \
    const uint32_t srowoff = (r0 + (lane & 15)) * 128, lsw = (lane & 7) << 4, lhi = (lane >> 4) << 4, lsw2 = (lane & 6) << 3; \
    (void)g; (void)t; (void)srowoff; (void)lsw; (void)lhi; (void)lsw2;
    uint32_t stgp = 0, peer;
    asm volatile("mapa.shared::cluster.u32 %0, %1, %2;" : "=r"(peer) : "r"(sbase), "r"(rank ^ 1));
    peer -= sbase;
    const uint32_t dA0 = (((sbase & 0x3FFFF) + wg * 8192) >> 4) | 0x10000u, dB0 = ((sbase & 0x3FFFF) >> 4) | 0x2000000u;
#define DESC(lo, hi) ((uint64_t)(uint32_t)(lo) | ((uint64_t)(hi) << 32))
#define STG_ARRIVE() { __syncwarp(); if (elect_one()) mbar_arrive_local(bar_stg); }
#define STG_WAIT() { mbar_wait(bar_stg, stgp); stgp ^= 1; }
#define PROFS() do {} while (0)
#define REL(addr) { if (elect_one()) { mbar_arrive_local(addr); asm volatile("mbarrier.arrive.shared::cluster.b64 _, [%0];" :: "r"((addr) + peer) : "memory"); } }
#define QSTEP(ACC, DA, SC) { \
      const uint32_t da = (DA), db = dB0 + (ub & 0x18) * (QST >> 7); \
      mbar_wait(ub, par); \
      wgmma_fence(); \
      wgmma4_n192<SC>(ACC, da, db); \
      wgmma_commit(); PROFS(); }
#define QREL() { wgmma_wait<1>(); REL(ub + 376); ub += 8; }
#define RA_CUR (dA0 + (OFF_RA >> 4) + (ub & 0x18) * (SLOT >> 7))
#define PUMP1() { QSTEP(S1, RA_CUR, 1); QREL(); }
#define PUMPN() { wgmma_fence(); wgmma4_n192<1>(S1, RA_CUR, dB0 + (ub & 0x18) * (QST >> 7)); wgmma_commit(); PROFS(); QREL(); }
#define PUMP0() { PUMP1(); SCHED_FENCE(); }
#define WSTEP() { \
      const uint32_t s4 = (ub - bar_full - 256) >> 1; \
      const uint32_t da = dA0 + (((uint32_t)(WO_ASLOT(par) >> s4) & 15) << 10), db = dB0 + (((uint32_t)(WO_BSLOT >> s4) & 15) << 10); \
      mbar_wait(ub, par); \
      wgmma_fence(); \
      wgmma4_n128<1>(S1, da, db); \
      wgmma_commit(); PROFS(); \
      wgmma_wait<1>(); \
      if (s4) REL(ub + 376); \
      ub += 8; }
#define PUMPS(n) { _Pragma("unroll 1") for (int i_ = 0; i_ < (n); i_++) PUMP1(); }
#define LNSTEP(ACC, hh) { wgmma_fence(); wgmma_n192<1, 0>(ACC, make_desc(sbase + OFF_LNA + wg * 1024, 0, 128) ^ (1ull << 62), make_desc(sbase + OFF_LNB + (hh) * 4096, 0, 128) ^ (1ull << 62)); }
#define WARP_STORE(tm, tile, col, row) { fence_proxy_async_smem(); __syncwarp(); WARP_STORE0(tm, tile, col, row); }
#define WARP_STORE0(tm, tile, col, row) { \
      if (elect_one()) { tma_store_2d(tm, (tile) + r0 * 128, col, (row) + r0); asm volatile("cp.async.bulk.commit_group;" ::: "memory"); } __syncwarp(); }
#define TILE_CONSTS(base, on, bit) \
      uint32_t ta[5]; \
      { PMASKS(on, bit); (void)pbit; ta[4] = pm0; } \
      _Pragma("unroll") for (int j = 0; j < 4; j++) ta[j] = (base) + srowoff + ((((uint32_t)j << 5) + lhi) ^ lsw); \
      PINU(ta, 5); SCHED_FENCE(); \
      const uint32_t pm0 = ta[4], pbit = (bit)
#define X_OUT(pc, W) { \
      _Pragma("unroll") for (int j = 0; j < 4; j++) \
        stsm_x4(ta[j] + (pc) * SLOT, \
                PBIT(pack_bf16((W)[j * 8 + 0], (W)[j * 8 + 1])), PBIT(pack_bf16((W)[j * 8 + 2], (W)[j * 8 + 3])), \
                (pack_bf16((W)[j * 8 + 4], (W)[j * 8 + 5])), (pack_bf16((W)[j * 8 + 6], (W)[j * 8 + 7]))); }
#define REST_P1(SKEW) { \
      mbar_wait(bar_stat2, par); \
      LNSTEP(S1, 1); \
      wgmma_commit(); \
      _Pragma("unroll 1") while (ub < bar_full + 256) { \
        const bool hold = ub == bar_full + 256 - 8 * (SKEW) && wg == 0; \
        if (hold) { wgmma_wait<0>(); REL(ub + 376); bar_sync<BAR_SKEW, 256>(); } \
        QSTEP(S1, RA_CUR, 1); \
        if (ub == bar_full + 248 && wg == 1) bar_arrive<BAR_SKEW, 256>(); \
        wgmma_wait<1>(); if (!hold) REL(ub + 376); ub += 8; \
      } \
      mbar_wait(bar_done + (31 - (SKEW)) * 8, par);        \
      wgmma_wait<0>(); \
      ACC_FENCE(S1, 96); \
      REL(bar_done + 31 * 8); \
      PROF(13); }
#define FOLD(tile, rd) { \
          LANE_CONSTS(); \
          float d[32]; \
          ACC_DEF(d, 32); \
          mbar_wait(bar_phi, 0); \
          wgmma_fence(); \
          _Pragma("unroll") for (int i = 0; i < 2; i++) { \
            const uint64_t da = make_desc((tile) + wg * 8192 + i * 64, 16, 1024); \
            const uint64_t db = make_desc(sbase + OFF_PHI + wg * 4096 + i * 2048, 16, 512) ^ (3ull << 62); \
            wgmma_n32<0>(d + i * 16, da, db); wgmma_n32<1>(d + i * 16, da + 2, db + 64); \
          } \
          wgmma_commit(); \
          PUMP0(); \
          ACC_FENCE(d, 32); \
          bar_wg(wg); \
          _Pragma("unroll") for (int i = 0; i < 4; i++) { \
            const float* x = d + (i & 1) * 8 + (i >> 1) * 2; \
            if (rd) sts128((tile) + wg * 8192 + ((warp & 3) * 16 + (i >> 1) * 8 + g) * 128 + (((2 * t + (i & 1)) ^ g) << 4), \
                           pack_bf16(x[0], x[1]), pack_bf16(x[4], x[5]), pack_bf16(x[16], x[17]), pack_bf16(x[20], x[21])); \
            else stsm_x4((tile) + srowoff + ((((uint32_t)i << 5) + lhi) ^ lsw), pack_bf16(d[i * 8], d[i * 8 + 1]), pack_bf16(d[i * 8 + 2], d[i * 8 + 3]), \
                         pack_bf16(d[i * 8 + 4], d[i * 8 + 5]), pack_bf16(d[i * 8 + 6], d[i * 8 + 7])); \
          } \
          }
#define XM_ISSUE() { mbar_wait(bar_xr, par); wgmma_fence(); \
      wgmma_copy(T_, dA0 + (OFF_RA >> 4), make_desc(sbase + OFF_ID, 128, 128) ^ (1ull << 62)); }
#define COPYN(d, s, n) _Pragma("unroll") for (int i_ = 0; i_ < (n); i_++) { uint32_t c_; asm volatile("mov.b32 %0, %1;" : "=r"(c_) : "f"((s)[i_])); (d)[i_] = __uint_as_float(c_); }
#define COPY64(d, s) COPYN(d, s, 64)
#define XM_DONE() { ACC_FENCE(T_, 64); COPY64(S1, T_); ACC_FENCE(S1, 64); \
      __syncwarp(); if (elect_one()) mbar_arrive_local(bar_lx); }
#define LOAD_X() { float T_[64]; ACC_DEF(T_, 64); wgmma_wait<0>(); XM_ISSUE(); wgmma_commit(); wgmma_wait<0>(); XM_DONE(); }

    float S0[96], S1[96];
    if (lane == 0) epoch0 = ld_relaxed(prm.epoch);
    __syncwarp();
    uint32_t ub = bar_full;
    {
      constexpr int l = 0;
      constexpr uint32_t par = 0;
      (void)l;
      ACC_DEF(S0, 96);
      QSTEP(S0, RA_CUR, 0);
      PROF(0);
      SCHED_FENCE();
      cluster_wait();
      ub += 8;
#pragma unroll 1
      for (int i = 1; i < 5; i++) {
        QSTEP(S0, dA0 + (OFF_RA >> 4) + i * (SLOT >> 4), 1);
        QREL();
      }
    }
    const unsigned epoch = __shfl_sync(0xffffffffu, epoch0, 0), ep1 = epoch + 1;
#pragma unroll 1
    for (int l = 0;; l++) {
      const uint32_t par = l & 1;
      PROF(1);
      {
        LANE_CONSTS();
        uint32_t ta[4];
#pragma unroll
        for (int j = 0; j < 4; j++) ta[j] = pK + srowoff + ((((uint32_t)j << 5) + lhi) ^ lsw);
        float p0, p1, a0 = 0.f, a1 = 0.f, q0 = 0.f, q1 = 0.f;
#define STATS(j0, j1) _Pragma("unroll") for (int j = (j0); j < (j1); j++) { \
          uint32_t x[4]; \
          ldsm_x4(ta[j & 3] + (j >> 2) * SLOT, x[0], x[1], x[2], x[3]); \
          if (j == 0) { p0 = __shfl_sync(0xffffffffu, bf_lo(x[0]), lane & 28); p1 = __shfl_sync(0xffffffffu, bf_lo(x[1]), lane & 28); } \
          _Pragma("unroll") for (int i = 0; i < 4; i += 2) { \
            const float d0 = bf_lo(x[i]) - p0, d1 = bf_hi(x[i]) - p0, d2 = bf_lo(x[i + 1]) - p1, d3 = bf_hi(x[i + 1]) - p1; \
            a0 += d0 + d1; a1 += d2 + d3; \
            q0 = fmaf(d1, d1, fmaf(d0, d0, q0)); q1 = fmaf(d3, d3, fmaf(d2, d2, q1)); } } \
          asm volatile("" : "+f"(a0), "+f"(a1), "+f"(q0), "+f"(q1), "+f"(p0), "+f"(p1)); SCHED_FENCE()
        if (SB0) { STATS(0, SB0); }
        bar_wg(wg);
        QSTEP(S0, dA0 + ((OFF_S + SLOT) >> 4), 1);
        QREL();
        SCHED_FENCE();
        STATS(SB0, SB1);
        ACC_DEF(S1, 96);
        QSTEP(S1, dA0 + (OFF_S >> 4), 0);
        QREL();
        SCHED_FENCE();
        STATS(SB1, SB2);
        QSTEP(S1, dA0 + ((OFF_S + SLOT) >> 4), 1);
        QREL();
        SCHED_FENCE();
        STATS(SB2, 8);
#pragma unroll
        for (int o = 1; o <= 2; o <<= 1) {
          a0 += __shfl_xor_sync(0xffffffffu, a0, o); a1 += __shfl_xor_sync(0xffffffffu, a1, o);
          q0 += __shfl_xor_sync(0xffffffffu, q0, o); q1 += __shfl_xor_sync(0xffffffffu, q1, o);
        }
        if (t == 1) { a0 = a1; q0 = q1; p0 = p1; }
        if (t < 2) st_b64(g_stats + (size_t)(mm * 128 + r0 + g + t * 8) * 8 + jj, __float_as_uint(fmaf(a0, 1.f / 128.f, p0)),
                          (__float_as_uint(fmaxf(fmaf(a0 * (-1.f / 128.f), a0, q0), 0.f)) & ~3u) | STAT_TAG(l));
        if (l) { asm volatile("cp.async.bulk.wait_group 0;" ::: "memory"); bar_arrive<BAR_X1, 288>(); }
#pragma unroll 1
        while (ub < bar_full + 144) {
          QSTEP(S0, RA_CUR, 1);
          if (ub == bar_full + 64) PROF(2);
          QREL();
        }
      }
      LANE_CONSTS();
      mbar_wait(bar_stat, par);
      LNSTEP(S0, 0);
      wgmma_commit();
      const float rs0 = lds32f(sbase + OFF_ST + (r0 + g) * 4), rs1 = lds32f(sbase + OFF_ST + (r0 + g + 8) * 4);
      PUMP0();
      ACC_FENCE(S0, 96);
      PROF(3);
      if (!par) {
        constexpr uint32_t par = 0;
        uint32_t qa[16];
        uint32_t kf[24], vf[24];
#define DRAIN_A(ACC, hp, PMP) { \
          LANE_CONSTS(); \
          FRAG(kf, ACC + 32, 0, (hp) * 2); \
          PMP; \
          FRAG(vf, ACC + 64, 1, (hp) * 2 + 1); \
          _Pragma("unroll") for (int i_ = 0; i_ < 16; i_++) qa[i_] = pack_bf16(ACC[2 * i_], ACC[2 * i_ + 1]); \
          PINU(qa, 16); }
        DRAIN_A(S0, 0, PUMP0());
        if (l == 0 && NLAYERS > 1) {
#pragma unroll 1
          for (int rd = 1; rd >= 0; rd--) {
            FOLD(sbase + (12 - rd) * SLOT, rd);
            asm volatile("bar.arrive %0, 288;" :: "r"(BAR_WF + 1 - rd) : "memory");
          }
        }
        PUMPS(FPUMP);
#pragma unroll 1
        for (int h = 0; h < 2; h++) {
          PROFH(4, 16);
          LANE_CONSTS();
          FRAG_PUT(kf + 16, 0); FRAG_PUT(vf + 16, 1);
          STG_ARRIVE();
          if (h) { PROF(8); LOAD_X(); PROF(9); WSTEP(); PROF(10); } else PUMPS(HPUMP2);
          const bool gt0 = 2 * t > g, gt1 = 2 * t >= g;
          uint32_t msk[2] = {(gt0 ? 0xFFFFu : 0u) | (gt1 ? 0xFFFF0000u : 0u), g == 2 * t ? 0x10001u : 0u};
          PINU(msk, 2);
          TILE_CONSTS(sbase, false, 0);
          (void)pm0; (void)pbit;
          if (h) PROF(12);
          STG_WAIT();
          if (h) PROF(14);
          if (warp < 2) mbar_wait(bar_halo, h);
          if (h) PROF(15);
          if (h == 0) mbar_wait(ub, par);
          FRAG_GET(kf, 0);
          PROFH(5, 17);
          float s[2][3][4];
#pragma unroll
          for (int ks = 0; ks < 2; ks++)
#pragma unroll
            for (int i = 0; i < 6; i++) {
              const int hh = i & 1, jb = 2 - (i >> 1);
              const uint32_t* b = kf + jb * 8 + hh * 4 + ks * 2;
              if (ks) mma_bf16(s[hh][jb], qa[hh * 8 + 4], qa[hh * 8 + 5], qa[hh * 8 + 6], qa[hh * 8 + 7], b[0], b[1]);
              else mma_bf16_z(s[hh][jb], qa[hh * 8], qa[hh * 8 + 1], qa[hh * 8 + 2], qa[hh * 8 + 3], b[0], b[1]);
            }
          if (h == 0) PUMPN()
          PROFH(6, 18);
          float va[2][2], vb[2][2], mx[2][2];
#pragma unroll
          for (int hh = 0; hh < 2; hh++) {
            va[hh][0] = gt0 ? s[hh][0][0] : s[hh][1][0];
            vb[hh][0] = gt1 ? s[hh][0][1] : s[hh][1][1];
            va[hh][1] = gt0 ? s[hh][1][2] : s[hh][2][2];
            vb[hh][1] = gt1 ? s[hh][1][3] : s[hh][2][3];
          }
          if (warp < 2 && mm == 0) {
#pragma unroll
            for (int hh = 0; hh < 2; hh++) { if (gt0) va[hh][0] = -INFINITY; if (gt1) vb[hh][0] = -INFINITY; }
          }
#pragma unroll
          for (int i = 0; i < 4; i++) mx[i >> 1][i & 1] = fmaxf(va[i >> 1][i & 1], vb[i >> 1][i & 1]);
#pragma unroll
          for (int o = 1; o <= 2; o <<= 1)
#pragma unroll
            for (int i = 0; i < 4; i++) mx[i >> 1][i & 1] = fmaxf(mx[i >> 1][i & 1], __shfl_xor_sync(0xffffffffu, mx[i >> 1][i & 1], o));
          const float sc0 = rs0 * (0.17677669529663687f * LOG2E), sc1 = rs1 * (0.17677669529663687f * LOG2E);
#pragma unroll
          for (int i = 0; i < 4; i++) {
            const float sc = (i & 1) ? sc1 : sc0, m = mx[i >> 1][i & 1];
            va[i >> 1][i & 1] = ex2((va[i >> 1][i & 1] - m) * sc); vb[i >> 1][i & 1] = ex2((vb[i >> 1][i & 1] - m) * sc);
            mx[i >> 1][i & 1] = va[i >> 1][i & 1] + vb[i >> 1][i & 1];
          }
          if (h == 0) { PIN(&va[0][0], 4); PIN(&vb[0][0], 4); PIN(&mx[0][0], 4); PUMP1(); }
          if (h) PROF(20);
          if (warp < 2) mbar_wait(bar_halo + 8, h);
          if (h) PROF(21);
          if (h == 0) mbar_wait(ub, par);
          FRAG_GET(vf, 1);
#pragma unroll
          for (int o = 1; o <= 2; o <<= 1)
#pragma unroll
            for (int i = 0; i < 4; i++) mx[i >> 1][i & 1] += __shfl_xor_sync(0xffffffffu, mx[i >> 1][i & 1], o);
          float o[8][4];
          uint32_t pa[4][2];
#pragma unroll
          for (int i = 0; i < 4; i++) {
            const float iv = rcp_fast(mx[i >> 1][i & 1]);
            const uint32_t w = pack_bf16(va[i >> 1][i & 1] * iv, vb[i >> 1][i & 1] * iv);
            pa[i][0] = w & msk[0]; pa[i][1] = w & ~msk[0];
          }
          PROFH(7, 19);
#pragma unroll
          for (int i = 7; i >= 0; i--) {
            const uint32_t* a = vf + (i >> 2) * 8 + (i & 3) * 2;
            mma_bf16_z(o[i], a[0], a[1], a[8], a[9], pa[(i & 2) + (i >> 2)][0], pa[(i & 2) + (i >> 2)][1]);
          }
          if (h == 0) PUMPN() else mbar_wait(bar_done + 30 * 8, par);
          if (NLAYERS > 1 && l + h == 0) mbar_wait(bar_phi + 8, 0);
          if (h) PROF(22);
          {
            const uint32_t pm0 = msk[1], pbit = O_BIT(l) * 0x10001u;
#pragma unroll
            for (int i = 0; i < 4; i++)
              stsm_x4_t(ta[i] + (h ? 3 : 12) * SLOT, PBIT(pack_bf16(o[i][0], o[i][1])), PBIT(pack_bf16(o[i + 4][0], o[i + 4][1])),
                        pack_bf16(o[i][2], o[i][3]), pack_bf16(o[i + 4][2], o[i + 4][3]));
          }
          WARP_STORE(&tm_os, sbase + (h ? 3 : 12) * SLOT, jj * 128 + h * 64, mm * 128);
          PROFH(11, 23);
          if (h) break;
          REST_P1(ASKEW);
          asm volatile("cp.async.bulk.wait_group.read 0;" ::: "memory");
          DRAIN_A(S1, 1, {});
        }
      } else {
        constexpr uint32_t par = 1;
        float st[32];
        const float c0 = rs0 * LOG2E, c1 = rs1 * LOG2E;
        { V_ADDR(pV, 0); STAGE_V(S0 + 64); }
        if (warp < 2) sts128(sbase + OFF_ONES + warp * 512 + lane * 16, 0x3F803F80u, 0x3F803F80u, 0x3F803F80u, 0x3F803F80u);
        scale32(st, S0, c0, c1);
        PIN(st, 32);
#define PHI_PIECE(c) { \
          e_[2 * (c)] = ex2(st[2 * (c)]); e_[2 * (c) + 1] = ex2(st[2 * (c) + 1]); \
          _Pragma("unroll") for (int k_ = 4 * (c); k_ < 4 * (c) + 4; k_++) m_[(c) >> 1] = (k_ & 7) ? fmaf(st[k_], st[k_], m_[(c) >> 1]) : st[k_] * st[k_]; \
          asm volatile("" : "+f"(e_[2 * (c)]), "+f"(e_[2 * (c) + 1]), "+f"(m_[(c) >> 1])); SCHED_FENCE(); }
#define PHI_FIN() { \
          big = __any_sync(0xffffffffu, !(fmaxf(fmaxf(m_[0], m_[1]), fmaxf(m_[2], m_[3])) < BIGLIM)); \
          if (__builtin_expect(big, 0)) { COPYN(e_, st, 16); } \
          _Pragma("unroll") for (int k_ = 0; k_ < 16; k_++) st[k_] = e_[k_]; \
          PIN(st, 16); }
#define KV_MMA(vs, IL) { \
          const uint32_t dp = dA0 + 12 * 1024 - wg * 2560, dv = dA0 + (vs) * 1024 + ((OFF_ONES - (vs) * SLOT - 16) << 12) - wg * (512 << 16); \
          STG_WAIT(); \
          fence_proxy_async_smem(); \
          wgmma_fence(); \
          _Pragma("unroll") for (int ks = 0; ks < 8; ks++) { \
            const uint64_t a = DESC(dp + ks * 128, 0x40000040), b = DESC(dv + ks * (64 - (64 << 16)), 0x80000020); \
            if ((IL) && ks) wgmma_fence(); \
            if (ks == 0) wgmma_n40<0, 1>(kv, a, b); else wgmma_n40<1, 1>(kv, a, b); \
            if (ks == 7) wgmma_commit(); \
            if (IL) PHI_PIECE(ks); } }
#define KV_RED1(i) if (h) red_v4(g_kv[l >> 1] + (jj * 4) * KVH + warp * 768 + lane * 4 + (i) * 128, S0[32 + (i) * 3], S0[33 + (i) * 3], S0[34 + (i) * 3], 1.f)
#define KV_REDS(n) { _Pragma("unroll") for (int i_ = 0; i_ < 6; i_++) if (((RPACE >> (4 * i_)) & 15) == (n)) KV_RED1(i_); }
#define KV_SEND(kp) { \
          float sd[9]; \
          _Pragma("unroll") for (int i = 0; i < 8; i++) { (kp)[i] = kv[i]; sd[i] = kv[8 + i]; } \
          (kp)[8] = rank ? kv[18] : kv[16]; sd[8] = rank ? kv[16] : kv[18]; \
          const uint32_t ra = sbase + peer + (warp * 32 + lane) * 4, rb = bar_kx + peer; \
          if (elect_one()) mbar_expect_tx(bar_kx, 1152); \
          _Pragma("unroll") for (int i = 0; i < 2; i++) \
            asm volatile("st.async.weak.shared::cluster.mbarrier::complete_tx::bytes.v4.f32 [%0], {%1, %2, %3, %4}, [%5];" \
                         :: "r"(ra + (warp * 32 + lane) * 12 + OFF_PHI + i * 4096), "f"(sd[4 * i]), "f"(sd[4 * i + 1]), "f"(sd[4 * i + 2]), "f"(sd[4 * i + 3]), "r"(rb) : "memory"); \
          asm volatile("st.async.weak.shared::cluster.mbarrier::complete_tx::bytes.f32 [%0], %1, [%2];" :: "r"(ra + OFF_LNB), "f"(sd[8]), "r"(rb) : "memory"); }
#define KV_RECV(kp, hp) { \
          float r_[9]; \
          float* kvg = g_kv[l >> 1] + (jj * 4 + (hp) * 2) * KVH + warp * 768 + rank * 384 + lane * 4; \
          mbar_wait(bar_kx, l >> 1); \
          _Pragma("unroll") for (int i = 0; i < 2; i++) \
            asm volatile("ld.shared.v4.f32 {%0, %1, %2, %3}, [%4];" : "=f"(r_[4 * i]), "=f"(r_[4 * i + 1]), "=f"(r_[4 * i + 2]), "=f"(r_[4 * i + 3]) \
                         : "r"(sbase + OFF_PHI + i * 4096 + (warp * 32 + lane) * 16) : "memory"); \
          r_[8] = lds32f(sbase + OFF_LNB + (warp * 32 + lane) * 4); \
          _Pragma("unroll") for (int i = 0; i < 3; i++) red_v4(kvg + i * 128, (kp)[3 * i] + r_[3 * i], (kp)[3 * i + 1] + r_[3 * i + 1], (kp)[3 * i + 2] + r_[3 * i + 2], 2.f); }
#define KV_LOAD(hp) { \
          const uint4* kvg = reinterpret_cast<const uint4*>(g_kv[l >> 1] + (jj * 4 + (hp) * 2) * KVH) + warp * 192 + lane; \
          _Pragma("unroll") for (int i = 0; i < 6; i++) v[i] = ld_b128(kvg + i * 32); }
#define KVV(i) __uint_as_float((i) % 3 == 0 ? v[(i) / 3].x : ((i) % 3 == 1 ? v[(i) / 3].y : v[(i) / 3].z))
#define KV_TILE(hp) { \
          _Pragma("unroll 1") for (int it = 0; it < (1 << 16); it++) { \
            if (__all_sync(0xffffffffu, (v[0].w & v[1].w & v[2].w & v[3].w & v[4].w & v[5].w) == 0x41800000u)) break; \
            RETRY_COUNT(); \
            KV_LOAD(hp); \
          } \
          if (hp) PROF(26); else PROF(25); \
          const uint32_t e = lane & 7, jt = ((lane >> 1) & 4) + (e >> 1); \
          const uint32_t row = ((((warp >> 1) ^ wg) & 1) << 5) + ((jt & 1) << 4) + ((warp & 1) << 3) + (jt & 6) + (e & 1); \
          const uint32_t kd = pV + wg * 8192 + row * 128, ksw = (row & 7) << 4; \
          _Pragma("unroll") for (int i = 0; i < 2; i++) \
            stsm_x4(kd + ((i * 32 + lhi) ^ ksw), pack_bf16(KVV(i * 9), KVV(i * 9 + 1)), pack_bf16(KVV(i * 9 + 2), KVV(i * 9 + 3)), \
                    pack_bf16(KVV(i * 9 + 4), KVV(i * 9 + 5)), pack_bf16(KVV(i * 9 + 6), KVV(i * 9 + 7))); \
          stsm_x4(kd + ((64u + lhi) ^ ksw), pack_bf16(KVV(8), 1.f), pack_bf16(KVV(17), 1.f), 0u, 0u); }
#pragma unroll 1
        for (int h = 0; h < 2; h++) {
          PROFH(4, 6);
          PUMP0();
          LANE_CONSTS();
          const uint32_t dsw = (uint32_t)(g ^ (2 * t)) << 4, dst = ((t & 2) ? pK : sbase + 12 * SLOT) + (r0 + g) * 128;
          float e[16], f[16];
          KV_REDS(1);
          float sa = exps16_<0>(e, st);
          exps16_fix<0>(e, st, sa);
          asm volatile("" : "+f"(sa)); PIN(e, 16); PUMP0();
          if (h) STG_WAIT();
          KV_REDS(2);
          store16(e, sa, dst, dsw, 4);
          float sb = exps16_<1>(f, st);
          exps16_fix<1>(f, st, sb);
          asm volatile("" : "+f"(sb)); PIN(f, 16); PUMP0();
          KV_REDS(3);
          store16(f, sb, dst, dsw, 0);
          float sc = exps16_<0>(e, st + 2);
          exps16_fix<0>(e, st + 2, sc);
          asm volatile("" : "+f"(sc)); PIN(e, 16); PUMP0();
          KV_REDS(4);
          store16(e, sc, dst + 1024, dsw, 4);
          float sd = exps16_<1>(f, st + 2);
          exps16_fix<1>(f, st + 2, sd);
          asm volatile("" : "+f"(sd)); PIN(f, 16); PUMP0();
          store16(f, sd, dst + 1024, dsw, 0);
          PROFH(5, 7);
          if (h) break;
          {
            float kv[20];
            ACC_DEF(kv, 20);
            STG_ARRIVE();
            float e_[16], m_[4];
            KV_MMA(11, 0);
            PUMP0();
            ACC_FENCE(kv, 20);
            STG_ARRIVE();
            scale32(st, S0 + 32, c0, c1);
            PIN(st, 32);
            {
              COPYN(S0 + 32, kv, 8); COPYN(S0 + 40, kv + 16, 1); COPYN(S0 + 41, kv + 8, 8); COPYN(S0 + 49, kv + 18, 1);
              const int h = 1;
              KV_REDS(0);
            }
          }
        }
        bool big;
        uint4 v[6];
        {
          float kv[20];
          { LANE_CONSTS(); KV_LOAD(0); }
          mbar_wait(bar_stat2, par);
          ub = bar_full + 240;
          LNSTEP(S1, 1);
          PUMP1();
          if (wg == 0) bar_sync<BAR_SKEW, 256>();
          QSTEP(S1, RA_CUR, 1);
          if (wg == 1) bar_arrive<BAR_SKEW, 256>();
          QREL();
          { LANE_CONSTS(); KV_TILE(0); }
          LANE_CONSTS();
          V_ADDR(sbase + 3 * SLOT, rank * 32);
          PINU(va_, 2);
          mbar_wait(bar_done + 30 * 8, par);
          wgmma_wait<0>();
          ACC_FENCE(S1, 96);
          PROF(13);
          STAGE_V(S1 + 64);
          STG_ARRIVE();
          REL(bar_done + 31 * 8);
          scale32(st, S1, c0, c1);
          PIN(st, 32);
          PROF(16);
          ACC_DEF(kv, 20);
          float e_[16], m_[4];
          KV_MMA(3, 1);
          SCHED_FENCE();
          PROF(14);
          PHI_FIN();
          SCHED_FENCE();
          PROF(15);
          wgmma_wait<0>();
          ACC_FENCE(kv, 20);
          PROF(12);
          { float kp[9]; KV_SEND(kp); _Pragma("unroll") for (int i = 0; i < 3; i++) v[i] = make_uint4(__float_as_uint(kp[3 * i]), __float_as_uint(kp[3 * i + 1]), __float_as_uint(kp[3 * i + 2]), 0u); }
#define VDEF(i0) _Pragma("unroll") for (int i = (i0); i < 6; i++) asm volatile("" : "=r"(v[i].x), "=r"(v[i].y), "=r"(v[i].z), "=r"(v[i].w))
          VDEF(3);
          PROF(17);
        }
#pragma unroll 1
        for (int h = 0; h < 2; h++) {
          const uint32_t pO = sbase + (h ? 3 : 8) * SLOT;
          LANE_CONSTS();
          uint32_t fq[32];
          if (h) { KV_LOAD(1); phiq_a(st, big); PIN(st, 16); PROF(31); }
          PROFH(18, 32);
          SCHED_FENCE();
          phiq_b<1>(fq, st, big); PINU(fq, 16); PIN(st + 16, 16);
          SCHED_FENCE();
          PROFH(8, 9);
          if (h) {
            asm volatile("cp.async.bulk.wait_group.read 0;" ::: "memory");
            mbar_wait(bar_lx, par);
            PROF(30);
            KV_TILE(1);
            STG_ARRIVE();
          }
          SCHED_FENCE();
          if (h == 0) {
            float kp[9];
#pragma unroll
            for (int i = 0; i < 9; i++) kp[i] = KVV(i);
            KV_RECV(kp, 1);
            SCHED_FENCE();
          }
          phiq_b<0>(fq + 16, st + 16, big); PINU(fq + 16, 16);
          PROFH(10, 21);
          if (h) { STG_WAIT(); fence_proxy_async_smem(); }
          wgmma_wait<0>();
          ACC_FENCE(S1, 64);
          PROFH(19, 33);
          float o[4][20];
#define O_MMA(hh) { \
            const uint64_t db = make_desc(pV + (hh) * 8192, 16, 1024); \
            ACC_DEF(o[(hh) * 2], 20); ACC_DEF(o[(hh) * 2 + 1], 20); \
            wgmma_fence(); \
            wgmma_n40_rs<0>(o[(hh) * 2], fq + (hh) * 16, db + 256); wgmma_n40_rs<0>(o[(hh) * 2 + 1], fq + (hh) * 16 + 8, db); \
            wgmma_n40_rs<1>(o[(hh) * 2], fq + (hh) * 16 + 4, db + 384); wgmma_n40_rs<1>(o[(hh) * 2 + 1], fq + (hh) * 16 + 12, db + 128); \
            wgmma_commit(); }
          O_MMA(0);
          SCHED_FENCE();
          PMASKS(true, O_BIT(l));
#pragma unroll
          for (int hh = 0; hh < 2; hh++) {
            wgmma_wait<0>();
            ACC_FENCE(o[hh * 2], 20); ACC_FENCE(o[hh * 2 + 1], 20);
            if (!hh) { O_MMA(1); SCHED_FENCE(); }
            if (hh) PROFH(22, 24);
            const float* x = o[hh * 2];
            const float* y = o[hh * 2 + 1];
            const float sx0 = x[17] * 0x1p-40f, sy0 = y[17] * 0x1p-40f, sx1 = x[19] * 0x1p-40f, sy1 = y[19] * 0x1p-40f;
            const float i0 = rcp_fast(fmaf(fmaf(x[17], 1e-6f, x[16]), sy0, y[16] * sx0)), i1 = rcp_fast(fmaf(fmaf(x[19], 1e-6f, x[18]), sy1, y[18] * sx1));
            const float ax0 = sy0 * i0, ay0 = sx0 * i0, ax1 = sy1 * i1, ay1 = sx1 * i1;
#pragma unroll
            for (int dp = 0; dp < 2; dp++)
              stsm_x4(pO + srowoff + ((hh * 64 + dp * 32 + lhi) ^ lsw),
                      PBIT(pack_bf16(fmaf(x[dp * 8], ax0, y[dp * 8] * ay0), fmaf(x[dp * 8 + 1], ax0, y[dp * 8 + 1] * ay0))),
                      PBIT(pack_bf16(fmaf(x[dp * 8 + 2], ax1, y[dp * 8 + 2] * ay1), fmaf(x[dp * 8 + 3], ax1, y[dp * 8 + 3] * ay1))),
                      (pack_bf16(fmaf(x[dp * 8 + 4], ax0, y[dp * 8 + 4] * ay0), fmaf(x[dp * 8 + 5], ax0, y[dp * 8 + 5] * ay0))),
                      (pack_bf16(fmaf(x[dp * 8 + 6], ax1, y[dp * 8 + 6] * ay1), fmaf(x[dp * 8 + 7], ax1, y[dp * 8 + 7] * ay1))));
          }
          WARP_STORE(&tm_os, pO, jj * 128 + h * 64, mm * 128);
          PROFH(20, 34);
          if (h) break;
          float T_[64];
          scale32(st, S1 + 32, c0, c1);
          PIN(st, 32);
          ACC_DEF(T_, 64);
          XM_ISSUE(); wgmma_commit();
          SCHED_FENCE();
          big = any_big(st);
          SCHED_FENCE();
          PROF(27);
          wgmma_wait<0>(); XM_DONE();
          PROF(28);
          bar_wg(wg);
          WSTEP();
          SCHED_FENCE();
          VDEF(0);
          PROF(29);
        }
      }
      __syncwarp();
      if (elect_one()) mbar_arrive_local(bar_epi);
      bar_wg(wg);
#pragma unroll 1
      while (ub < bar_full + 384) {
        if (FSK && l == NLAYERS - 1 && wg == 0 && ub == bar_full + 384 - 8 * FSK) bar_sync<BAR_SKEW, 256>();
        if (FSK && l == NLAYERS - 1 && wg == 1 && ub == bar_full + 376) { mbar_wait(ub, par); bar_arrive<BAR_SKEW, 256>(); }
        WSTEP();
        if (ub == bar_full + 8 * 41) { asm volatile("cp.async.bulk.wait_group.read 0;" ::: "memory"); PROF(35); }
        if (ub == bar_full + 8 * 42) PROF(36);
      }
      {
        float Wb[32];
        LANE_CONSTS();
        TILE_CONSTS(pK, l < NLAYERS - 1, X_BIT(l));
        if (l < NLAYERS - 1) mbar_wait(bar_full, par ^ 1);
        wgmma_wait<0>();
        ACC_FENCE(S1, 64);
        COPYN(Wb, S1 + 32, 32);
        PROF(37);
        uint32_t xa[16];
#pragma unroll
        for (int i = 0; i < 16; i++) { const uint32_t w = pack_bf16(S1[2 * i], S1[2 * i + 1]); xa[i] = (i & 2) ? w : PBIT(w); }
        PINU(xa, 16);
#define XA_OUT() _Pragma("unroll") for (int j = 0; j < 4; j++) stsm_x4(ta[j], xa[4 * j], xa[4 * j + 1], xa[4 * j + 2], xa[4 * j + 3])
        if (l == NLAYERS - 1) {
          XA_OUT();
          const uint32_t src = pK + (r0 + (lane >> 3)) * 128 + (((lane ^ (lane >> 3)) & 7) << 4);
          uint4* dst = reinterpret_cast<uint4*>(prm.out + (size_t)(mm * 128 + (warp >> 1) * 32 + (warp & 1) + (lane >> 3) * 2) * D_MODEL + jj * 128) + (lane & 7);
#pragma unroll
          for (int pc = 0; pc < 2; pc++) {
            if (pc) { PMASKS(false, 0); X_OUT(1, Wb); }
            __syncwarp();
            uint4 y[4];
#pragma unroll
            for (int i = 0; i < 4; i++)
              asm volatile("ld.shared.v4.u32 {%0, %1, %2, %3}, [%4];" : "=r"(y[i].x), "=r"(y[i].y), "=r"(y[i].z), "=r"(y[i].w) : "r"((src + pc * SLOT + i * 512) ^ ((i & 1) << 6)) : "memory");
#pragma unroll
            for (int i = 0; i < 4; i++) dst[pc * 8 + i * 1024] = y[i];
            if (pc) PROF(39); else PROF(38);
          }
          break;
        }
        PROF(38);
        XA_OUT();
        ACC_DEF(S0, 96);
        wgmma_fence();
        wgmma_n192_rs<0>(S0, xa, dB0);
#pragma unroll
        for (int k = 1; k < RSK; k++) wgmma_n192_rs<1>(S0, xa + 4 * k, dB0 + 128 * k);
        wgmma_commit();
        WARP_STORE(&tm_os, pK, jj * 128, mm * 128 + S_LEN);
        if (RSK < 4) {
          wgmma_fence();
#pragma unroll
          for (int k = RSK; k < 4; k++) wgmma_n192_rs<1>(S0, xa + 4 * k, dB0 + 128 * k);
          wgmma_commit();
        }
        { const int ln_ = l + 1, l = ln_; const uint32_t ub = bar_full; (void)l; (void)ub; PROFS(); }
        REL(bar_done + 47 * 8);
        ub = bar_full + 8;
        PROF(39);
        { PMASKS(false, 0); X_OUT(1, Wb); }
        fence_proxy_async_smem();
      }
    }
    cluster_sync();
    if (threadIdx.x == 0) PROFT(487);
  }
}

typedef CUresult (*PFN_encode)(CUtensorMap*, CUtensorMapDataType, cuuint32_t, void*, const cuuint64_t*, const cuuint64_t*,
                               const cuuint32_t*, const cuuint32_t*, CUtensorMapInterleave, CUtensorMapSwizzle,
                               CUtensorMapL2promotion, CUtensorMapFloatOOBfill);

CUtensorMap make_map(PFN_encode enc, const void* ptr, uint64_t inner, uint64_t outer, uint32_t box_inner, uint32_t box_outer,
                     CUtensorMapSwizzle swz = CU_TENSOR_MAP_SWIZZLE_128B, int promo = CU_TENSOR_MAP_L2_PROMOTION_L2_256B) {
  CUtensorMap m;
  cuuint64_t dims[2] = {inner, outer};
  cuuint64_t strides[1] = {inner * 2};
  cuuint32_t box[2] = {box_inner, box_outer};
  cuuint32_t es[2] = {1, 1};
  enc(&m, CU_TENSOR_MAP_DATA_TYPE_BFLOAT16, 2, const_cast<void*>(ptr), dims, strides, box, es, CU_TENSOR_MAP_INTERLEAVE_NONE,
      swz, (CUtensorMapL2promotion)promo, CU_TENSOR_MAP_FLOAT_OOB_FILL_NONE);
  return m;
}

CUtensorMap make_tile_map(PFN_encode enc, const void* ptr, uint64_t rows, bool by_parity, int promo) {
  CUtensorMap m;
  cuuint64_t dims[4] = {D_MODEL, 16, 2, rows / 32};
  cuuint64_t strides[3] = {by_parity ? 4096u : 2048u, by_parity ? 2048u : 32768u, 65536};
  cuuint32_t box[4] = {64, 16, 2, 4};
  cuuint32_t es[4] = {1, 1, 1, 1};
  enc(&m, CU_TENSOR_MAP_DATA_TYPE_BFLOAT16, 4, const_cast<void*>(ptr), dims, strides, box, es, CU_TENSOR_MAP_INTERLEAVE_NONE,
      CU_TENSOR_MAP_SWIZZLE_128B, (CUtensorMapL2promotion)promo, CU_TENSOR_MAP_FLOAT_OOB_FILL_NONE);
  return m;
}

}

extern "C" void kernel_launch(void* const* d_in, const int* in_sizes, int n_in, void* d_out, int out_size) {
  (void)in_sizes; (void)n_in; (void)out_size;
  static PFN_encode enc = nullptr;
  if (!enc) {
    void* fn = nullptr;
    cudaDriverEntryPointQueryResult qr;
    cudaGetDriverEntryPoint("cuTensorMapEncodeTiled", &fn, cudaEnableDefault, &qr);
    enc = (PFN_encode)fn;
    cudaFuncSetAttribute(mega_kernel, cudaFuncAttributeMaxDynamicSharedMemorySize, SMEM_BYTES);
  }
  Params prm;
  prm.wA_o = (const __nv_bfloat16*)d_in[2];
  prm.wB_qkv = (const __nv_bfloat16*)d_in[4];
  prm.wB_o = (const __nv_bfloat16*)d_in[6];
  prm.out = (__nv_bfloat16*)d_out;
  void *obuf = nullptr, *wf = nullptr, *fl = nullptr;
  cudaGetSymbolAddress(&fl, g_flags);
  prm.epoch = &static_cast<Flags*>(fl)->epoch.v;
  cudaGetSymbolAddress(&obuf, g_obuf);
  cudaGetSymbolAddress(&wf, g_wfold);
  CUtensorMap tm_x0 = make_tile_map(enc, d_in[0], S_LEN, true, XPROMO);
  CUtensorMap tm_os = make_map(enc, obuf, D_MODEL, 2 * S_LEN, 64, 16);
  CUtensorMap tm_o = make_tile_map(enc, obuf, 2 * S_LEN, false, OPROMO);
  CUtensorMap tm_wf = make_map(enc, wf, 2048, D_MODEL, 64, 32);
  CUtensorMap tm_wqA = make_map(enc, d_in[1], 3 * D_MODEL, D_MODEL, 64, 32, CU_TENSOR_MAP_SWIZZLE_128B, WPROMO);
  CUtensorMap tm_wqB = make_map(enc, prm.wB_qkv, 3 * D_MODEL, D_MODEL, 64, 32);
  CUtensorMap tm_woA = make_map(enc, prm.wA_o, D_MODEL, D_MODEL, 64, 64);
  CUtensorMap tm_woB = make_map(enc, prm.wB_o, D_MODEL, D_MODEL, 64, 64);
  CUtensorMap tm_phi = make_map(enc, d_in[5], 32, 1024, 32, 128, CU_TENSOR_MAP_SWIZZLE_64B);
  mega_kernel<<<NMAIN + NAUX, 384, SMEM_BYTES>>>(prm, tm_x0, tm_os, tm_o, tm_wf, tm_wqA, tm_wqB, tm_woA, tm_woB, tm_phi);
}
```

```cpp
#include <cuda_runtime.h>
#include <cuda.h>
#include <cuda_bf16.h>
#include <stdint.h>

#define NLAYERS 4

#define HPUMP2 1
#define ASKEW 2
#define FPUMP 3
#define PFGAP 100
#define POLLGAP 120
#define HW1 30
#define XPACE 0x06050401000000ull
#define HW0 18
#define XD 4
#define WFGAP 10
#define EARLY 4
#define BIGLIM 3600.f
#define SUMLO 0x1p-100f
#define SUMHI 0x1p100f
#define XPROMO 2
#define OPROMO 3
#define STAG2 0
#define WPROMO 3
#define SB0 2
#define SB1 4
#define SB2 6
#define PROWS 7
#define SPD0 0
#define SPD1 0
#define SPD2 300
#define FRB 0x3535353535ull
#define NOB 0xFFFFFF00u
#define NO1 ~0u
#define NOX ~0u
#define FD0 3
#define CSGAP 300
#define AUXORD 0x76543210
#define FSK 3
#define OWNW0 1
#define OWNW1 2
#define RPACE 0x221100
#define RSK 2
namespace {

constexpr int S_LEN = 2048, D_MODEL = 1024;
constexpr int NAUX = 4, NMAIN = 128;
constexpr int SLOT = 16384;
constexpr int QST = 24576;
constexpr int OFF_RA = 6 * SLOT, OFF_S = 10 * SLOT;
constexpr int OFF_HALO = 13 * SLOT, OFF_LNB = OFF_HALO  , OFF_ONES = OFF_HALO + 3072;
constexpr int OFF_ST = OFF_HALO + 7168  , OFF_ID = OFF_HALO + 7680, OFF_PHI = OFF_HALO + 8192;
constexpr int OFF_BAR = 14 * SLOT;
constexpr int OFF_LNA = OFF_BAR + 1024;
constexpr int SMEM_BYTES = OFF_LNA + 2048;
#define WO_ASLOT(par) ((par) ? 0x9876CAB39876CA98ull : 0xBC7698A3BC7698BCull)
constexpr unsigned long long WO_BSLOT = 0x5432105421054210ull;
__device__ __forceinline__ int srcb(int j, int i) { return (i + (i >= j)) & 7; }
__device__ __forceinline__ int kslice(int j, int i) { return i < 2 ? 2 * j + i : (i < 9 ? 2 * srcb(j, i - 2) : 2 * srcb(j, i - 9) + 1); }
__device__ __forceinline__ int wslice(int j, int s) { return 2 * ((s & 7) ? srcb(j, (s & 7) - 1) : j) + (s >> 3); }
constexpr int KVH = 6 * 128 * 4;

struct __align__(128) Flag { unsigned v; unsigned pad[31]; };
struct Flags {
  Flag xready[4][16];
  Flag wfready[8];
  Flag done;
  Flag epoch;
};

__device__ Flags g_flags;
__device__ __nv_bfloat16 g_obuf[2 * S_LEN * D_MODEL];
#define O_BIT(l) ((epoch * NLAYERS + (l) + 1) & 1u)
#define X_BIT(l) ((epoch * (NLAYERS - 1) + (l) + 1) & 1u)
__device__ __nv_bfloat16 g_wfold[D_MODEL * 2048];
__device__ uint4 g_halo[16 * 8 * 512];
__device__ __align__(128) float g_kv[2][32 * KVH];
__device__ __align__(128) uint2 g_colsum[2][1536][2];
__device__ __align__(128) uint2 g_stats[S_LEN * 8];
#define H_BIT(l) (NLAYERS > 2 ? (uint32_t)((l) == 0) : (ep1 & 1))
#define STAT_TAG(l) ((ep1 * NLAYERS + (l) + 1) & 3u)

#define RETRY_COUNT()
#define PRL 3
#define PROFL 1
#define PROFW 0
#define PROF2V() do {} while (0)
#define PROFT(i) do {} while (0)
#define PROF(i) do {} while (0)
#define PROFH(i, j) do {} while (0)
#define PROFL3(i) do {} while (0)

__device__ __forceinline__ uint32_t smem_u32(const void* p) { return (uint32_t)__cvta_generic_to_shared(p); }
__device__ __forceinline__ bool elect_one() {
  uint32_t p;
  asm volatile("{\n.reg .pred p;\nelect.sync _|p, 0xffffffff;\nselp.u32 %0, 1, 0, p;\n}\n" : "=r"(p));
  return p != 0;
}
__device__ __forceinline__ void mbar_init(uint32_t bar, uint32_t cnt) {
  asm volatile("mbarrier.init.shared::cta.b64 [%0], %1;" :: "r"(bar), "r"(cnt));
}
__device__ __forceinline__ void mbar_expect_tx(uint32_t bar, uint32_t bytes) {
  asm volatile("mbarrier.arrive.expect_tx.shared::cta.b64 _, [%0], %1;" :: "r"(bar), "r"(bytes) : "memory");
}
#define mbar_wait(bar, parity) \
  asm volatile("{\n.reg .pred p, q;\nW_%=:\nmbarrier.try_wait.parity.shared::cta.b64 p, [%1], %2;\nadd.s32 %0, %0, -1;\n" \
               "setp.gt.and.s32 q, %0, 0, !p;\n@q bra.uni W_%=;\n}\n" : "+r"(budget) : "r"((uint32_t)(bar)), "r"((uint32_t)(parity)) : "memory")
#define mbar_wait_sl(bar, parity) \
  asm volatile("{\n.reg .pred p, q;\nW_%=:\nmbarrier.try_wait.parity.shared::cta.b64 p, [%1], %2, 20000;\nadd.s32 %0, %0, -64;\n" \
               "setp.gt.and.s32 q, %0, 0, !p;\n@q bra.uni W_%=;\n}\n" : "+r"(budget) : "r"((uint32_t)(bar)), "r"((uint32_t)(parity)) : "memory")
__device__ __forceinline__ void mbar_arrive_local(uint32_t bar) {
  asm volatile("mbarrier.arrive.shared::cta.b64 _, [%0];" :: "r"(bar) : "memory");
}
__device__ __forceinline__ void tma_load_2d(uint32_t dst, const CUtensorMap* tm, uint32_t bar, int c0, int c1) {
  asm volatile("cp.async.bulk.tensor.2d.shared::cluster.global.mbarrier::complete_tx::bytes [%0], [%1, {%3, %4}], [%2];"
               :: "r"(dst), "l"(tm), "r"(bar), "r"(c0), "r"(c1) : "memory");
}
__device__ __forceinline__ void tma_load_2d_mc(uint32_t dst, const CUtensorMap* tm, uint32_t bar, int c0, int c1) {
  asm volatile("cp.async.bulk.tensor.2d.shared::cluster.global.mbarrier::complete_tx::bytes.multicast::cluster [%0], [%1, {%3, %4}], [%2], %5;"
               :: "r"(dst), "l"(tm), "r"(bar), "r"(c0), "r"(c1), "h"((uint16_t)3) : "memory");
}
__device__ __forceinline__ void tma_store_2d(const CUtensorMap* tm, uint32_t src, int c0, int c1) {
  asm volatile("cp.async.bulk.tensor.2d.global.shared::cta.bulk_group [%0, {%2, %3}], [%1];"
               :: "l"(tm), "r"(src), "r"(c0), "r"(c1) : "memory");
}
__device__ __forceinline__ void tma_load_t(uint32_t dst, const CUtensorMap* tm, uint32_t bar, int c0, int row) {
  asm volatile("cp.async.bulk.tensor.4d.shared::cluster.global.mbarrier::complete_tx::bytes [%0], [%1, {%3, %5, %5, %4}], [%2];"
               :: "r"(dst), "l"(tm), "r"(bar), "r"(c0), "r"(row >> 5), "r"(0) : "memory");
}
__device__ __forceinline__ void tma_store_t(const CUtensorMap* tm, uint32_t src, int c0, int row) {
  asm volatile("cp.async.bulk.tensor.4d.global.shared::cta.bulk_group [%0, {%2, %4, %4, %3}], [%1];"
               :: "l"(tm), "r"(src), "r"(c0), "r"(row >> 5), "r"(0) : "memory");
}
__device__ __forceinline__ void bulk_commit_wait() {
  asm volatile("cp.async.bulk.commit_group;\ncp.async.bulk.wait_group 0;" ::: "memory");
}
__device__ __forceinline__ void prefetch_tmap(const CUtensorMap* tm) {
  asm volatile("prefetch.tensormap [%0];" :: "l"(tm) : "memory");
}
__device__ __forceinline__ void fence_proxy_async_global() { asm volatile("fence.proxy.async.global;" ::: "memory"); }
__device__ __forceinline__ void fence_proxy_async_smem() { asm volatile("fence.proxy.async.shared::cta;" ::: "memory"); }
__device__ __forceinline__ unsigned ld_relaxed(const unsigned* p) {
  unsigned v;
  asm volatile("ld.relaxed.gpu.global.u32 %0, [%1];" : "=r"(v) : "l"(p) : "memory");
  return v;
}
__device__ __forceinline__ void fence_acquire() { asm volatile("fence.acquire.gpu;" ::: "memory"); }
__device__ __forceinline__ void wait_flag(const unsigned* p, unsigned target) {
  int it = 0;
  while ((int)(ld_relaxed(p) - target) < 0 && ++it < (1 << 20)) {}
  fence_acquire();
}
__device__ __forceinline__ void signal_release(unsigned* p) {
  asm volatile("red.release.gpu.global.add.u32 [%0], 1;" :: "l"(p) : "memory");
}
template <int ID, int N> __device__ __forceinline__ void bar_arrive() { asm volatile("bar.arrive %0, %1;" :: "n"(ID), "n"(N) : "memory"); }
template <int ID, int N> __device__ __forceinline__ void bar_sync() { asm volatile("bar.sync %0, %1;" :: "n"(ID), "n"(N) : "memory"); }
__device__ __forceinline__ void bar_wg(int wg) { asm volatile("bar.sync %0, 128;" :: "r"(2 + wg) : "memory"); }
__device__ __forceinline__ void cluster_sync() {
  asm volatile("barrier.cluster.arrive.relaxed.aligned;\nbarrier.cluster.wait.aligned;" ::: "memory");
}
__device__ __forceinline__ void cluster_wait() { asm volatile("barrier.cluster.wait.acquire.aligned;" ::: "memory"); }
enum { BAR_X1 = 7, BAR_WF = 8  , BAR_SKEW = 10 };

__device__ __forceinline__ void wgmma_fence() { asm volatile("wgmma.fence.sync.aligned;" ::: "memory"); }
__device__ __forceinline__ void wgmma_commit() { asm volatile("wgmma.commit_group.sync.aligned;" ::: "memory"); }
template <int N> __device__ __forceinline__ void wgmma_wait() { asm volatile("wgmma.wait_group.sync.aligned %0;" :: "n"(N) : "memory"); }

template <int scale_d, int tnsp_b = 1> __device__ __forceinline__ void wgmma_n192(float* d, uint64_t descA, uint64_t descB) {
  asm volatile("{\n.reg .pred p;\nsetp.ne.b32 p, %98, 0;\n"
               "wgmma.mma_async.sync.aligned.m64n192k16.f32.bf16.bf16 {%0,%1,%2,%3,%4,%5,%6,%7,%8,%9,%10,%11,%12,%13,%14,%15,%16,%17,%18,%19,%20,%21,%22,%23,%24,%25,%26,%27,%28,%29,%30,%31,%32,%33,%34,%35,%36,%37,%38,%39,%40,%41,%42,%43,%44,%45,%46,%47,%48,%49,%50,%51,%52,%53,%54,%55,%56,%57,%58,%59,%60,%61,%62,%63,%64,%65,%66,%67,%68,%69,%70,%71,%72,%73,%74,%75,%76,%77,%78,%79,%80,%81,%82,%83,%84,%85,%86,%87,%88,%89,%90,%91,%92,%93,%94,%95}, %96, %97, p, 1, 1, 0, %99;\n}\n"
               : "+f"(d[0]), "+f"(d[1]), "+f"(d[2]), "+f"(d[3]), "+f"(d[4]), "+f"(d[5]), "+f"(d[6]), "+f"(d[7]), "+f"(d[8]), "+f"(d[9]), "+f"(d[10]), "+f"(d[11]), "+f"(d[12]), "+f"(d[13]), "+f"(d[14]), "+f"(d[15]), "+f"(d[16]), "+f"(d[17]), "+f"(d[18]), "+f"(d[19]), "+f"(d[20]), "+f"(d[21]), "+f"(d[22]), "+f"(d[23]), "+f"(d[24]), "+f"(d[25]), "+f"(d[26]), "+f"(d[27]), "+f"(d[28]), "+f"(d[29]), "+f"(d[30]), "+f"(d[31]), "+f"(d[32]), "+f"(d[33]), "+f"(d[34]), "+f"(d[35]), "+f"(d[36]), "+f"(d[37]), "+f"(d[38]), "+f"(d[39]), "+f"(d[40]), "+f"(d[41]), "+f"(d[42]), "+f"(d[43]), "+f"(d[44]), "+f"(d[45]), "+f"(d[46]), "+f"(d[47]), "+f"(d[48]), "+f"(d[49]), "+f"(d[50]), "+f"(d[51]), "+f"(d[52]), "+f"(d[53]), "+f"(d[54]), "+f"(d[55]), "+f"(d[56]), "+f"(d[57]), "+f"(d[58]), "+f"(d[59]), "+f"(d[60]), "+f"(d[61]), "+f"(d[62]), "+f"(d[63]), "+f"(d[64]), "+f"(d[65]), "+f"(d[66]), "+f"(d[67]), "+f"(d[68]), "+f"(d[69]), "+f"(d[70]), "+f"(d[71]), "+f"(d[72]), "+f"(d[73]), "+f"(d[74]), "+f"(d[75]), "+f"(d[76]), "+f"(d[77]), "+f"(d[78]), "+f"(d[79]), "+f"(d[80]), "+f"(d[81]), "+f"(d[82]), "+f"(d[83]), "+f"(d[84]), "+f"(d[85]), "+f"(d[86]), "+f"(d[87]), "+f"(d[88]), "+f"(d[89]), "+f"(d[90]), "+f"(d[91]), "+f"(d[92]), "+f"(d[93]), "+f"(d[94]), "+f"(d[95])
               : "l"(descA), "l"(descB), "n"(scale_d), "n"(tnsp_b));
}
template <int scale_d> __device__ __forceinline__ void wgmma4_n192(float* d, uint32_t da, uint32_t db) {
#define R_ "{%0,%1,%2,%3,%4,%5,%6,%7,%8,%9,%10,%11,%12,%13,%14,%15,%16,%17,%18,%19,%20,%21,%22,%23,%24,%25,%26,%27,%28,%29,%30,%31,%32,%33,%34,%35,%36,%37,%38,%39,%40,%41,%42,%43,%44,%45,%46,%47,%48,%49,%50,%51,%52,%53,%54,%55,%56,%57,%58,%59,%60,%61,%62,%63,%64,%65,%66,%67,%68,%69,%70,%71,%72,%73,%74,%75,%76,%77,%78,%79,%80,%81,%82,%83,%84,%85,%86,%87,%88,%89,%90,%91,%92,%93,%94,%95}"
  asm volatile("{\n.reg .pred p, q;\n.reg .b64 a, b;\nsetp.ne.b32 p, %98, 0;\nsetp.eq.b32 q, 0, 0;\nmov.b64 a, {%96, 0x40000040};\nmov.b64 b, {%97, 0x40000040};\n"
               "wgmma.mma_async.sync.aligned.m64n192k16.f32.bf16.bf16 " R_ ", a, b, p, 1, 1, 0, 1;\nadd.s64 a, a, 2;\nadd.s64 b, b, 128;\n"
               "wgmma.mma_async.sync.aligned.m64n192k16.f32.bf16.bf16 " R_ ", a, b, q, 1, 1, 0, 1;\nadd.s64 a, a, 2;\nadd.s64 b, b, 128;\n"
               "wgmma.mma_async.sync.aligned.m64n192k16.f32.bf16.bf16 " R_ ", a, b, q, 1, 1, 0, 1;\nadd.s64 a, a, 2;\nadd.s64 b, b, 128;\n"
               "wgmma.mma_async.sync.aligned.m64n192k16.f32.bf16.bf16 " R_ ", a, b, q, 1, 1, 0, 1;\n}\n"
               : "+f"(d[0]), "+f"(d[1]), "+f"(d[2]), "+f"(d[3]), "+f"(d[4]), "+f"(d[5]), "+f"(d[6]), "+f"(d[7]), "+f"(d[8]), "+f"(d[9]), "+f"(d[10]), "+f"(d[11]), "+f"(d[12]), "+f"(d[13]), "+f"(d[14]), "+f"(d[15]), "+f"(d[16]), "+f"(d[17]), "+f"(d[18]), "+f"(d[19]), "+f"(d[20]), "+f"(d[21]), "+f"(d[22]), "+f"(d[23]), "+f"(d[24]), "+f"(d[25]), "+f"(d[26]), "+f"(d[27]), "+f"(d[28]), "+f"(d[29]), "+f"(d[30]), "+f"(d[31]), "+f"(d[32]), "+f"(d[33]), "+f"(d[34]), "+f"(d[35]), "+f"(d[36]), "+f"(d[37]), "+f"(d[38]), "+f"(d[39]), "+f"(d[40]), "+f"(d[41]), "+f"(d[42]), "+f"(d[43]), "+f"(d[44]), "+f"(d[45]), "+f"(d[46]), "+f"(d[47]), "+f"(d[48]), "+f"(d[49]), "+f"(d[50]), "+f"(d[51]), "+f"(d[52]), "+f"(d[53]), "+f"(d[54]), "+f"(d[55]), "+f"(d[56]), "+f"(d[57]), "+f"(d[58]), "+f"(d[59]), "+f"(d[60]), "+f"(d[61]), "+f"(d[62]), "+f"(d[63]), "+f"(d[64]), "+f"(d[65]), "+f"(d[66]), "+f"(d[67]), "+f"(d[68]), "+f"(d[69]), "+f"(d[70]), "+f"(d[71]), "+f"(d[72]), "+f"(d[73]), "+f"(d[74]), "+f"(d[75]), "+f"(d[76]), "+f"(d[77]), "+f"(d[78]), "+f"(d[79]), "+f"(d[80]), "+f"(d[81]), "+f"(d[82]), "+f"(d[83]), "+f"(d[84]), "+f"(d[85]), "+f"(d[86]), "+f"(d[87]), "+f"(d[88]), "+f"(d[89]), "+f"(d[90]), "+f"(d[91]), "+f"(d[92]), "+f"(d[93]), "+f"(d[94]), "+f"(d[95])
               : "r"(da), "r"(db), "n"(scale_d));
#undef R_
}
template <int scale_d> __device__ __forceinline__ void wgmma4_n128(float* d, uint32_t da, uint32_t db) {
#define R_ "{%0,%1,%2,%3,%4,%5,%6,%7,%8,%9,%10,%11,%12,%13,%14,%15,%16,%17,%18,%19,%20,%21,%22,%23,%24,%25,%26,%27,%28,%29,%30,%31,%32,%33,%34,%35,%36,%37,%38,%39,%40,%41,%42,%43,%44,%45,%46,%47,%48,%49,%50,%51,%52,%53,%54,%55,%56,%57,%58,%59,%60,%61,%62,%63}"
  asm volatile("{\n.reg .pred p, q;\n.reg .b64 a, b;\nsetp.ne.b32 p, %66, 0;\nsetp.eq.b32 q, 0, 0;\nmov.b64 a, {%64, 0x40000040};\nmov.b64 b, {%65, 0x40000040};\n"
               "wgmma.mma_async.sync.aligned.m64n128k16.f32.bf16.bf16 " R_ ", a, b, p, 1, 1, 0, 1;\nadd.s64 a, a, 2;\nadd.s64 b, b, 128;\n"
               "wgmma.mma_async.sync.aligned.m64n128k16.f32.bf16.bf16 " R_ ", a, b, q, 1, 1, 0, 1;\nadd.s64 a, a, 2;\nadd.s64 b, b, 128;\n"
               "wgmma.mma_async.sync.aligned.m64n128k16.f32.bf16.bf16 " R_ ", a, b, q, 1, 1, 0, 1;\nadd.s64 a, a, 2;\nadd.s64 b, b, 128;\n"
               "wgmma.mma_async.sync.aligned.m64n128k16.f32.bf16.bf16 " R_ ", a, b, q, 1, 1, 0, 1;\n}\n"
               : "+f"(d[0]), "+f"(d[1]), "+f"(d[2]), "+f"(d[3]), "+f"(d[4]), "+f"(d[5]), "+f"(d[6]), "+f"(d[7]), "+f"(d[8]), "+f"(d[9]), "+f"(d[10]), "+f"(d[11]), "+f"(d[12]), "+f"(d[13]), "+f"(d[14]), "+f"(d[15]), "+f"(d[16]), "+f"(d[17]), "+f"(d[18]), "+f"(d[19]), "+f"(d[20]), "+f"(d[21]), "+f"(d[22]), "+f"(d[23]), "+f"(d[24]), "+f"(d[25]), "+f"(d[26]), "+f"(d[27]), "+f"(d[28]), "+f"(d[29]), "+f"(d[30]), "+f"(d[31]), "+f"(d[32]), "+f"(d[33]), "+f"(d[34]), "+f"(d[35]), "+f"(d[36]), "+f"(d[37]), "+f"(d[38]), "+f"(d[39]), "+f"(d[40]), "+f"(d[41]), "+f"(d[42]), "+f"(d[43]), "+f"(d[44]), "+f"(d[45]), "+f"(d[46]), "+f"(d[47]), "+f"(d[48]), "+f"(d[49]), "+f"(d[50]), "+f"(d[51]), "+f"(d[52]), "+f"(d[53]), "+f"(d[54]), "+f"(d[55]), "+f"(d[56]), "+f"(d[57]), "+f"(d[58]), "+f"(d[59]), "+f"(d[60]), "+f"(d[61]), "+f"(d[62]), "+f"(d[63])
               : "r"(da), "r"(db), "n"(scale_d));
#undef R_
}
template <int scale_d> __device__ __forceinline__ void wgmma_n32(float* d, uint64_t descA, uint64_t descB) {
  asm volatile("{\n.reg .pred p;\nsetp.ne.b32 p, %18, 0;\n"
               "wgmma.mma_async.sync.aligned.m64n32k16.f32.bf16.bf16 {%0,%1,%2,%3,%4,%5,%6,%7,%8,%9,%10,%11,%12,%13,%14,%15}, %16, %17, p, 1, 1, 0, 1;\n}\n"
               : "+f"(d[0]), "+f"(d[1]), "+f"(d[2]), "+f"(d[3]), "+f"(d[4]), "+f"(d[5]), "+f"(d[6]), "+f"(d[7]), "+f"(d[8]), "+f"(d[9]), "+f"(d[10]), "+f"(d[11]), "+f"(d[12]), "+f"(d[13]), "+f"(d[14]), "+f"(d[15])
               : "l"(descA), "l"(descB), "n"(scale_d));
}
template <int scale_d, int tnsp_a> __device__ __forceinline__ void wgmma_n40(float* d, uint64_t descA, uint64_t descB) {
  asm volatile("{\n.reg .pred p;\nsetp.ne.b32 p, %22, 0;\n"
               "wgmma.mma_async.sync.aligned.m64n40k16.f32.bf16.bf16 {%0,%1,%2,%3,%4,%5,%6,%7,%8,%9,%10,%11,%12,%13,%14,%15,%16,%17,%18,%19}, %20, %21, p, 1, 1, %23, 1;\n}\n"
               : "+f"(d[0]), "+f"(d[1]), "+f"(d[2]), "+f"(d[3]), "+f"(d[4]), "+f"(d[5]), "+f"(d[6]), "+f"(d[7]), "+f"(d[8]), "+f"(d[9]), "+f"(d[10]), "+f"(d[11]), "+f"(d[12]), "+f"(d[13]), "+f"(d[14]), "+f"(d[15]), "+f"(d[16]), "+f"(d[17]), "+f"(d[18]), "+f"(d[19])
               : "l"(descA), "l"(descB), "n"(scale_d), "n"(tnsp_a));
}
template <int scale_d> __device__ __forceinline__ void wgmma_n40_rs(float* d, const uint32_t* a, uint64_t descB) {
  asm volatile("{\n.reg .pred p;\nsetp.ne.b32 p, %25, 0;\n"
               "wgmma.mma_async.sync.aligned.m64n40k16.f32.bf16.bf16 {%0,%1,%2,%3,%4,%5,%6,%7,%8,%9,%10,%11,%12,%13,%14,%15,%16,%17,%18,%19}, {%20,%21,%22,%23}, %24, p, 1, 1, 1;\n}\n"
               : "+f"(d[0]), "+f"(d[1]), "+f"(d[2]), "+f"(d[3]), "+f"(d[4]), "+f"(d[5]), "+f"(d[6]), "+f"(d[7]), "+f"(d[8]), "+f"(d[9]), "+f"(d[10]), "+f"(d[11]), "+f"(d[12]), "+f"(d[13]), "+f"(d[14]), "+f"(d[15]), "+f"(d[16]), "+f"(d[17]), "+f"(d[18]), "+f"(d[19])
               : "r"(a[0]), "r"(a[1]), "r"(a[2]), "r"(a[3]), "l"(descB), "n"(scale_d));
}
__device__ __forceinline__ void wgmma_copy(float* d, uint32_t da, uint64_t descB) {
  asm volatile("{\n.reg .pred p;\n.reg .b64 a;\nsetp.ne.b32 p, 0, 0;\nmov.b64 a, {%64, 0x40000040};\n"
               "wgmma.mma_async.sync.aligned.m64n16k16.f32.bf16.bf16 {%0,%1,%2,%3,%4,%5,%6,%7}, a, %65, p, 1, 1, 0, 0;\nadd.s64 a, a, 2;\n"
               "wgmma.mma_async.sync.aligned.m64n16k16.f32.bf16.bf16 {%8,%9,%10,%11,%12,%13,%14,%15}, a, %65, p, 1, 1, 0, 0;\nadd.s64 a, a, 2;\n"
               "wgmma.mma_async.sync.aligned.m64n16k16.f32.bf16.bf16 {%16,%17,%18,%19,%20,%21,%22,%23}, a, %65, p, 1, 1, 0, 0;\nadd.s64 a, a, 2;\n"
               "wgmma.mma_async.sync.aligned.m64n16k16.f32.bf16.bf16 {%24,%25,%26,%27,%28,%29,%30,%31}, a, %65, p, 1, 1, 0, 0;\nadd.s64 a, a, 1018;\n"
               "wgmma.mma_async.sync.aligned.m64n16k16.f32.bf16.bf16 {%32,%33,%34,%35,%36,%37,%38,%39}, a, %65, p, 1, 1, 0, 0;\nadd.s64 a, a, 2;\n"
               "wgmma.mma_async.sync.aligned.m64n16k16.f32.bf16.bf16 {%40,%41,%42,%43,%44,%45,%46,%47}, a, %65, p, 1, 1, 0, 0;\nadd.s64 a, a, 2;\n"
               "wgmma.mma_async.sync.aligned.m64n16k16.f32.bf16.bf16 {%48,%49,%50,%51,%52,%53,%54,%55}, a, %65, p, 1, 1, 0, 0;\nadd.s64 a, a, 2;\n"
               "wgmma.mma_async.sync.aligned.m64n16k16.f32.bf16.bf16 {%56,%57,%58,%59,%60,%61,%62,%63}, a, %65, p, 1, 1, 0, 0;\n"
               "}\n"
               : "+f"(d[0]), "+f"(d[1]), "+f"(d[2]), "+f"(d[3]), "+f"(d[4]), "+f"(d[5]), "+f"(d[6]), "+f"(d[7]), "+f"(d[8]), "+f"(d[9]), "+f"(d[10]), "+f"(d[11]), "+f"(d[12]), "+f"(d[13]), "+f"(d[14]), "+f"(d[15]), "+f"(d[16]), "+f"(d[17]), "+f"(d[18]), "+f"(d[19]), "+f"(d[20]), "+f"(d[21]), "+f"(d[22]), "+f"(d[23]), "+f"(d[24]), "+f"(d[25]), "+f"(d[26]), "+f"(d[27]), "+f"(d[28]), "+f"(d[29]), "+f"(d[30]), "+f"(d[31]), "+f"(d[32]), "+f"(d[33]), "+f"(d[34]), "+f"(d[35]), "+f"(d[36]), "+f"(d[37]), "+f"(d[38]), "+f"(d[39]), "+f"(d[40]), "+f"(d[41]), "+f"(d[42]), "+f"(d[43]), "+f"(d[44]), "+f"(d[45]), "+f"(d[46]), "+f"(d[47]), "+f"(d[48]), "+f"(d[49]), "+f"(d[50]), "+f"(d[51]), "+f"(d[52]), "+f"(d[53]), "+f"(d[54]), "+f"(d[55]), "+f"(d[56]), "+f"(d[57]), "+f"(d[58]), "+f"(d[59]), "+f"(d[60]), "+f"(d[61]), "+f"(d[62]), "+f"(d[63])
               : "r"(da), "l"(descB));
}
template <int scale_d> __device__ __forceinline__ void wgmma_n192_rs(float* d, const uint32_t* a, uint32_t db) {
  asm volatile("{\n.reg .pred p;\n.reg .b64 b;\nsetp.ne.b32 p, %101, 0;\nmov.b64 b, {%100, 0x40000040};\n"
               "wgmma.mma_async.sync.aligned.m64n192k16.f32.bf16.bf16 {%0,%1,%2,%3,%4,%5,%6,%7,%8,%9,%10,%11,%12,%13,%14,%15,%16,%17,%18,%19,%20,%21,%22,%23,%24,%25,%26,%27,%28,%29,%30,%31,%32,%33,%34,%35,%36,%37,%38,%39,%40,%41,%42,%43,%44,%45,%46,%47,%48,%49,%50,%51,%52,%53,%54,%55,%56,%57,%58,%59,%60,%61,%62,%63,%64,%65,%66,%67,%68,%69,%70,%71,%72,%73,%74,%75,%76,%77,%78,%79,%80,%81,%82,%83,%84,%85,%86,%87,%88,%89,%90,%91,%92,%93,%94,%95}, {%96,%97,%98,%99}, b, p, 1, 1, 1;\n}\n"
               : "+f"(d[0]), "+f"(d[1]), "+f"(d[2]), "+f"(d[3]), "+f"(d[4]), "+f"(d[5]), "+f"(d[6]), "+f"(d[7]), "+f"(d[8]), "+f"(d[9]), "+f"(d[10]), "+f"(d[11]), "+f"(d[12]), "+f"(d[13]), "+f"(d[14]), "+f"(d[15]), "+f"(d[16]), "+f"(d[17]), "+f"(d[18]), "+f"(d[19]), "+f"(d[20]), "+f"(d[21]), "+f"(d[22]), "+f"(d[23]), "+f"(d[24]), "+f"(d[25]), "+f"(d[26]), "+f"(d[27]), "+f"(d[28]), "+f"(d[29]), "+f"(d[30]), "+f"(d[31]), "+f"(d[32]), "+f"(d[33]), "+f"(d[34]), "+f"(d[35]), "+f"(d[36]), "+f"(d[37]), "+f"(d[38]), "+f"(d[39]), "+f"(d[40]), "+f"(d[41]), "+f"(d[42]), "+f"(d[43]), "+f"(d[44]), "+f"(d[45]), "+f"(d[46]), "+f"(d[47]), "+f"(d[48]), "+f"(d[49]), "+f"(d[50]), "+f"(d[51]), "+f"(d[52]), "+f"(d[53]), "+f"(d[54]), "+f"(d[55]), "+f"(d[56]), "+f"(d[57]), "+f"(d[58]), "+f"(d[59]), "+f"(d[60]), "+f"(d[61]), "+f"(d[62]), "+f"(d[63]), "+f"(d[64]), "+f"(d[65]), "+f"(d[66]), "+f"(d[67]), "+f"(d[68]), "+f"(d[69]), "+f"(d[70]), "+f"(d[71]), "+f"(d[72]), "+f"(d[73]), "+f"(d[74]), "+f"(d[75]), "+f"(d[76]), "+f"(d[77]), "+f"(d[78]), "+f"(d[79]), "+f"(d[80]), "+f"(d[81]), "+f"(d[82]), "+f"(d[83]), "+f"(d[84]), "+f"(d[85]), "+f"(d[86]), "+f"(d[87]), "+f"(d[88]), "+f"(d[89]), "+f"(d[90]), "+f"(d[91]), "+f"(d[92]), "+f"(d[93]), "+f"(d[94]), "+f"(d[95])
               : "r"(a[0]), "r"(a[1]), "r"(a[2]), "r"(a[3]), "r"(db), "n"(scale_d));
}
__device__ __forceinline__ uint64_t make_desc(uint32_t addr, uint32_t lbo_bytes, uint32_t sbo_bytes) {
  return (uint64_t)((addr & 0x3FFFF) >> 4) | ((uint64_t)(lbo_bytes >> 4) << 16) | ((uint64_t)(sbo_bytes >> 4) << 32) | (1ull << 62);
}

__device__ __forceinline__ void ldsm_x4(uint32_t addr, uint32_t& r0, uint32_t& r1, uint32_t& r2, uint32_t& r3) {
  asm volatile("ldmatrix.sync.aligned.m8n8.x4.shared.b16 {%0,%1,%2,%3}, [%4];" : "=r"(r0), "=r"(r1), "=r"(r2), "=r"(r3) : "r"(addr) : "memory");
}
__device__ __forceinline__ void ldsm_x4_t(uint32_t addr, uint32_t& r0, uint32_t& r1, uint32_t& r2, uint32_t& r3) {
  asm volatile("ldmatrix.sync.aligned.m8n8.x4.trans.shared.b16 {%0,%1,%2,%3}, [%4];" : "=r"(r0), "=r"(r1), "=r"(r2), "=r"(r3) : "r"(addr) : "memory");
}
__device__ __forceinline__ void stsm_x4(uint32_t addr, uint32_t r0, uint32_t r1, uint32_t r2, uint32_t r3) {
  asm volatile("stmatrix.sync.aligned.m8n8.x4.shared.b16 [%0], {%1,%2,%3,%4};" :: "r"(addr), "r"(r0), "r"(r1), "r"(r2), "r"(r3) : "memory");
}
__device__ __forceinline__ void stsm_x4_t(uint32_t addr, uint32_t r0, uint32_t r1, uint32_t r2, uint32_t r3) {
  asm volatile("stmatrix.sync.aligned.m8n8.x4.trans.shared.b16 [%0], {%1,%2,%3,%4};" :: "r"(addr), "r"(r0), "r"(r1), "r"(r2), "r"(r3) : "memory");
}
__device__ __forceinline__ void sts128(uint32_t addr, uint32_t a, uint32_t b, uint32_t c, uint32_t d) {
  asm volatile("st.shared.v4.u32 [%0], {%1,%2,%3,%4};" :: "r"(addr), "r"(a), "r"(b), "r"(c), "r"(d) : "memory");
}
__device__ __forceinline__ float lds32f(uint32_t addr) {
  float v;
  asm volatile("ld.shared.f32 %0, [%1];" : "=f"(v) : "r"(addr) : "memory");
  return v;
}
__device__ __forceinline__ void sts32f(uint32_t addr, float a) {
  asm volatile("st.shared.f32 [%0], %1;" :: "r"(addr), "f"(a) : "memory");
}
__device__ __forceinline__ void mma_bf16(float (&c)[4], uint32_t a0, uint32_t a1, uint32_t a2, uint32_t a3, uint32_t b0, uint32_t b1) {
  asm volatile("mma.sync.aligned.m16n8k16.row.col.f32.bf16.bf16.f32 {%0,%1,%2,%3}, {%4,%5,%6,%7}, {%8,%9}, {%0,%1,%2,%3};"
               : "+f"(c[0]), "+f"(c[1]), "+f"(c[2]), "+f"(c[3]) : "r"(a0), "r"(a1), "r"(a2), "r"(a3), "r"(b0), "r"(b1));
}
__device__ __forceinline__ void mma_bf16_z(float (&c)[4], uint32_t a0, uint32_t a1, uint32_t a2, uint32_t a3, uint32_t b0, uint32_t b1) {
  asm volatile("mma.sync.aligned.m16n8k16.row.col.f32.bf16.bf16.f32 {%0,%1,%2,%3}, {%4,%5,%6,%7}, {%8,%9}, {%10,%10,%10,%10};"
               : "=f"(c[0]), "=f"(c[1]), "=f"(c[2]), "=f"(c[3]) : "r"(a0), "r"(a1), "r"(a2), "r"(a3), "r"(b0), "r"(b1), "f"(0.f));
}
__device__ __forceinline__ uint32_t movm_t(uint32_t v) {
  uint32_t r;
  asm volatile("movmatrix.sync.aligned.m8n8.trans.b16 %0, %1;" : "=r"(r) : "r"(v));
  return r;
}
__device__ __forceinline__ uint32_t pack_bf16(float lo, float hi) {
  uint32_t r;
  asm("cvt.rn.bf16x2.f32 %0, %1, %2;" : "=r"(r) : "f"(hi), "f"(lo));
  return r;
}
__device__ __forceinline__ float bf_lo(uint32_t v) { return __uint_as_float(v << 16); }
__device__ __forceinline__ float bf_hi(uint32_t v) { return __uint_as_float(v & 0xFFFF0000u); }
__device__ __forceinline__ void split3(float x, uint32_t& h, uint32_t& m, uint32_t& l) {
  h = pack_bf16(x, 0.f); x -= bf_lo(h);
  m = pack_bf16(x, 0.f); x -= bf_lo(m);
  l = pack_bf16(x, 0.f);
}
__device__ __forceinline__ float ex2(float x) { float r; asm("ex2.approx.ftz.f32 %0, %1;" : "=f"(r) : "f"(x)); return r; }
__device__ __forceinline__ float rcp_fast(float x) { float r; asm("rcp.approx.ftz.f32 %0, %1;" : "=f"(r) : "f"(x)); return r; }
__device__ __forceinline__ void red_v4(float* p, float a, float b, float c, float d) {
  asm volatile("red.global.add.v4.f32 [%0], {%1, %2, %3, %4};" :: "l"(p), "f"(a), "f"(b), "f"(c), "f"(d) : "memory");
}
__device__ __forceinline__ uint4 ld_ll(const uint4* p) {
  uint4 v;
  asm volatile("{\n.reg .b64 a, b;\nld.relaxed.gpu.global.v2.b64 {a, b}, [%4];\nmov.b64 {%0, %1}, a;\nmov.b64 {%2, %3}, b;\n}\n"
               : "=r"(v.x), "=r"(v.y), "=r"(v.z), "=r"(v.w) : "l"(p) : "memory");
  return v;
}
__device__ __forceinline__ void st_b64(uint2* p, uint32_t a, uint32_t b) {
  asm volatile("{\n.reg .b64 v;\nmov.b64 v, {%1, %2};\nst.relaxed.gpu.global.b64 [%0], v;\n}\n" :: "l"(p), "r"(a), "r"(b) : "memory");
}
__device__ __forceinline__ void st_b128(uint4* p, uint32_t a, uint32_t b, uint32_t c, uint32_t d) {
  asm volatile("{\n.reg .b128 v;\nmov.b128 v, {%1, %2, %3, %4};\nst.relaxed.gpu.global.b128 [%0], v;\n}\n" :: "l"(p), "r"(a), "r"(b), "r"(c), "r"(d) : "memory");
}
__device__ __forceinline__ uint4 ld_b128(const uint4* p) {
  uint4 v;
  asm volatile("{\n.reg .b128 v;\nld.relaxed.gpu.global.b128 v, [%4];\nmov.b128 {%0, %1, %2, %3}, v;\n}\n" : "=r"(v.x), "=r"(v.y), "=r"(v.z), "=r"(v.w) : "l"(p) : "memory");
  return v;
}

constexpr float LOG2E = 1.4426950408889634f;

struct Params {
  const __nv_bfloat16* wA_o;
  const __nv_bfloat16* wB_qkv;
  const __nv_bfloat16* wB_o;
  const unsigned* epoch;
  __nv_bfloat16* out;
};

#define ACC_DEF(d, n) _Pragma("unroll") for (int i_ = 0; i_ < (n); i_++) asm volatile("" : "=f"(d[i_]))
#define ACC_FENCE(d, n) _Pragma("unroll") for (int i_ = 0; i_ < (n); i_++) asm volatile("" : "+f"(d[i_]) :: "memory")
#define PIN(a, n) _Pragma("unroll") for (int i_ = 0; i_ < (n); i_++) asm volatile("" : "+f"((a)[i_]))
#define PINU(a, n) _Pragma("unroll") for (int i_ = 0; i_ < (n); i_++) asm volatile("" : "+r"((a)[i_]))

#define V_ADDR(p0, sw) uint32_t va_[2] = {(p0) + (srowoff >> 1) + (lhi ^ lsw2 ^ (sw)), (p0) + (srowoff >> 1) + ((32 + lhi) ^ lsw2 ^ (sw))}
#define STAGE_V(acc) { \
    _Pragma("unroll") for (int j_ = 0; j_ < 4; j_++) { \
      const float* a_ = (acc) + j_ * 8; \
      stsm_x4(va_[j_ & 1] + (j_ >> 1) * 8192, \
              pack_bf16(rs0 * a_[0], rs0 * a_[1]), pack_bf16(rs1 * a_[2], rs1 * a_[3]), pack_bf16(rs0 * a_[4], rs0 * a_[5]), pack_bf16(rs1 * a_[6], rs1 * a_[7])); } }
#define FRAG(dst, acc, TR, grp) { \
    _Pragma("unroll") for (int i_ = 15; i_ >= 0; i_--) { \
      const float r_ = (i_ & 8) ? rs1 : rs0; \
      const uint32_t w_ = pack_bf16(r_ * (acc)[4 * (i_ & 7) + (i_ >> 3) * 2], r_ * (acc)[4 * (i_ & 7) + (i_ >> 3) * 2 + 1]); \
      (dst)[8 + i_] = (TR) ? movm_t(w_) : w_; \
      if (i_ == 8 && warp >= 6 && mm < 15) { \
        _Pragma("unroll") for (int j_ = 0; j_ < 2; j_++) \
          st_b128(g_halo + (size_t)(mm * 8 + jj) * 512 + ((grp) * 4 + warp * 2 - 12 + j_) * 32 + lane, ((dst)[16 + j_ * 4] & ~1u) | H_BIT(l), (dst)[17 + j_ * 4], (dst)[18 + j_ * 4], (dst)[19 + j_ * 4]); } } \
    PINU((dst) + 8, 16); }
#define FRAG_PUT(src, slot) if (warp < 6) { _Pragma("unroll") for (int j_ = 0; j_ < 2; j_++) \
      sts128(sbase + OFF_S + (slot) * 8192 + 2048 + warp * 1024 + j_ * 512 + lane * 16, (src)[j_ * 4], (src)[j_ * 4 + 1], (src)[j_ * 4 + 2], (src)[j_ * 4 + 3]); }
#define FRAG_GET(dst, slot) { _Pragma("unroll") for (int j_ = 0; j_ < 2; j_++) \
      asm volatile("ld.shared.v4.u32 {%0, %1, %2, %3}, [%4];" : "=r"((dst)[j_ * 4]), "=r"((dst)[j_ * 4 + 1]), "=r"((dst)[j_ * 4 + 2]), "=r"((dst)[j_ * 4 + 3]) \
                   : "r"(sbase + OFF_S + (slot) * 8192 + warp * 1024 + j_ * 512 + lane * 16) : "memory"); }
#define RW(j) (((j) >> 1) * 4 + ((j) & 1))
template <int POS> __device__ __forceinline__ float exps16_(float* o, const float* p) {
  float s[4];
#pragma unroll
  for (int j = 0; j < 16; j++) { o[j] = ex2(POS ? p[RW(j)] : -p[RW(j)]); if (j < 4) s[j] = o[j]; else s[j & 3] += o[j]; }
  const float r = (s[0] + s[1]) + (s[2] + s[3]);
  return r + __shfl_xor_sync(0xffffffffu, r, 1);
}
template <int POS> __device__ __forceinline__ void exps16_fix(float* o, const float* p, float& sum) {
  if (__builtin_expect(__any_sync(0xffffffffu, !(sum > SUMLO && sum < SUMHI)), 0)) {
    float m = p[0], q[32];
#pragma unroll
    for (int j = 1; j < 16; j++) m = POS ? fmaxf(m, p[RW(j)]) : fminf(m, p[RW(j)]);
    const float x = __shfl_xor_sync(0xffffffffu, m, 1);
    m = POS ? fmaxf(m, x) : fminf(m, x);
#pragma unroll
    for (int j = 0; j < 16; j++) q[RW(j)] = p[RW(j)] - m;
    sum = exps16_<POS>(o, q);
  }
}
__device__ __forceinline__ void store16(const float* e, float sum, uint32_t dst, uint32_t dsw, int c0) {
  const float inv = rcp_fast(sum);
#pragma unroll
  for (int j = 0; j < 2; j++)
    sts128(dst + (((c0 + j) << 4) ^ dsw), pack_bf16(e[j * 8] * inv, e[j * 8 + 1] * inv), pack_bf16(e[j * 8 + 2] * inv, e[j * 8 + 3] * inv),
           pack_bf16(e[j * 8 + 4] * inv, e[j * 8 + 5] * inv), pack_bf16(e[j * 8 + 6] * inv, e[j * 8 + 7] * inv));
}
template <int POS> __device__ __forceinline__ void expp16(uint32_t* o, float* p) {
  {
#pragma unroll
    for (int r = 0; r < 4; r += 2) {
      float m = p[r];
#pragma unroll
      for (int j = 1; j < 8; j++) m = POS ? fmaxf(m, p[r + RW(j)]) : fminf(m, p[r + RW(j)]);
#pragma unroll
      for (int s = 1; s <= 2; s <<= 1) { const float x = __shfl_xor_sync(0xffffffffu, m, s); m = POS ? fmaxf(m, x) : fminf(m, x); }
#pragma unroll
      for (int j = 0; j < 8; j++) p[r + RW(j)] -= m;
    }
  }
#pragma unroll
  for (int j = 0; j < 8; j++) o[j] = pack_bf16(ex2(POS ? p[2 * j] : -p[2 * j]), ex2(POS ? p[2 * j + 1] : -p[2 * j + 1]));
}
__device__ __forceinline__ void scale32(float* o, const float* p, float c0, float c1) {
#pragma unroll
  for (int i = 0; i < 32; i++) asm volatile("mul.f32 %0, %1, %2;" : "=f"(o[i]) : "f"(p[i]), "f"((i & 2) ? c1 : c0));
}
__device__ __forceinline__ bool any_big(const float* p) {
  float m[4];
#pragma unroll
  for (int i = 0; i < 32; i++) m[i >> 3] = (i & 7) ? fmaf(p[i], p[i], m[i >> 3]) : p[i] * p[i];
  return __any_sync(0xffffffffu, !(fmaxf(fmaxf(m[0], m[1]), fmaxf(m[2], m[3])) < BIGLIM));
}
__device__ __forceinline__ void phiq_a(float* p, bool big) {
  if (__builtin_expect(!big, 1)) {
#pragma unroll
    for (int j = 0; j < 16; j++) p[j] = ex2(p[j]);
  }
}
template <int NEXT> __device__ __forceinline__ void phiq_b(uint32_t* o, float* p, bool big) {
  if (__builtin_expect(big, 0)) {
    expp16<0>(o, p); expp16<1>(o + 8, p);
  } else {
    if (NEXT) phiq_a(p + 16, false);
#pragma unroll
    for (int j = 0; j < 4; j++) {
      const float a = p[4 * j], b = p[4 * j + 1], c = p[4 * j + 2], d = p[4 * j + 3];
      const float ab = a * b, cd = c * d, r = rcp_fast(ab * cd), x = r * cd, y = r * ab;
      o[2 * j] = pack_bf16(x * b, x * a); o[2 * j + 1] = pack_bf16(y * d, y * c);
      o[8 + 2 * j] = pack_bf16(a, b); o[9 + 2 * j] = pack_bf16(c, d);
    }
  }
}
#define SCHED_FENCE() asm volatile("pmevent 0;" ::: "memory")

__global__ void __cluster_dims__(2, 1, 1) __launch_bounds__(384, 1)
mega_kernel(const Params prm  , const __grid_constant__ CUtensorMap tm_x0, const __grid_constant__ CUtensorMap tm_os,
            const __grid_constant__ CUtensorMap tm_o, const __grid_constant__ CUtensorMap tm_wf,
            const __grid_constant__ CUtensorMap tm_wqA, const __grid_constant__ CUtensorMap tm_wqB,
            const __grid_constant__ CUtensorMap tm_woA, const __grid_constant__ CUtensorMap tm_woB,
            const __grid_constant__ CUtensorMap tm_phi) {
  extern __shared__ __align__(1024) uint8_t smem_raw[];
  const uint32_t sbase = smem_u32(smem_raw);
  const uint32_t bar_full = sbase + OFF_BAR;
  const uint32_t bar_done = bar_full + 384;
  const uint32_t bar_stat = bar_full + 768, bar_stat2 = bar_full + 776, bar_epi = bar_full + 784, bar_phi = bar_full + 936  , bar_halo = bar_full + 904  ;
  const uint32_t bar_xr = bar_full + 800, bar_lx = bar_full + 808, bar_stg = bar_full + 832;
  const uint32_t bar_chk = bar_full + 848;

  const int warp = __shfl_sync(0xffffffffu, threadIdx.x >> 5, 0), lane = threadIdx.x & 31;
  const uint32_t bar_kx = sbase + OFF_ID + 384 + warp * 8;
  uint32_t rank;
  asm volatile("mov.u32 %0, %%cluster_ctarank;" : "=r"(rank));
  const int aux = (int)blockIdx.x - NMAIN, tp = (int)(blockIdx.x >> 1) - 4;
  const int gp = tp < 0 ? 0 : (tp < 32 ? tp & 7 : 1 + (tp - 32) % 7), me = tp < 0 ? tp + 8 : (tp < 32 ? tp >> 3 : 4 + (tp - 32) / 7);
  const int jj = me, cc = gp;
  const int cta = aux >= 0 ? -1 : (cc * 8 + jj) * 2 + (int)rank;
  const int mm = cc * 2 + (int)rank;

#define LOAD_EPOCH() const unsigned epoch = ld_relaxed(prm.epoch), ep1 = epoch + 1; (void)epoch
  int budget = 1 << 22;
  unsigned epoch0 = 0;

  if (cta >= 0) {
    if (warp >= 8 && warp < 10 && elect_one()) {
      const int u = warp - 8;
      const uint32_t fb = bar_full + u * 8;
      mbar_init(fb, 1);
      asm volatile("fence.mbarrier_init.release.cluster;" ::: "memory");
      fence_proxy_async_smem();
      mbar_expect_tx(fb, QST + SLOT);
      if (STAG2 && u) __nanosleep(STAG2);
      tma_load_t(sbase + OFF_RA + u * SLOT, &tm_x0, fb, srcb(jj, u) * 128, mm * 128);
#pragma unroll
      for (int i = 0; i < 6; i++) tma_load_2d(sbase + u * QST + i * 4096, &tm_wqA, fb, jj * 128 + (i >> 1) * 1024, srcb(jj, u) * 128 + (i & 1) * 32);
      PROFT(472 + u);
    }
    __syncwarp();
    if (elect_one()) {
#pragma unroll
      for (int i = 0; i < 4; i++) {
        const int u = warp * 4 + i;
        mbar_init(u < 2 ? bar_kx : bar_full + u * 8, ((u >= 4 && u < 11) || (u > 32 && u != 40)) ? 2 : 1); mbar_init(bar_done + u * 8, 16);
      }
      mbar_init(bar_stat + warp * 16, 0x111111181182ull >> (4 * warp) & 15);
      mbar_init(bar_stat + warp * 16 + 8, 0x111111121811ull >> (4 * warp) & 15);
      mbar_init(bar_chk + 112 + (warp & 7) * 8, 1);
      mbar_init(bar_kx, 1);
      asm volatile("fence.mbarrier_init.release.cluster;" ::: "memory");
    }
    __syncwarp();
    if (threadIdx.x == 383) epoch0 = ld_relaxed(prm.epoch);
    if (PRL == 0 && lane == 0 && warp >= 8) PROFT(440 + warp - 8);
    __syncthreads();
    if (PRL == 0 && threadIdx.x == 256) PROFT(444);
    asm volatile("barrier.cluster.arrive.relaxed.aligned;" ::: "memory");
  }

  if (cta < 0) {
    LOAD_EPOCH();
    const uint32_t buf = sbase + warp * SLOT, bar = sbase + OFF_BAR + warp * 16;
    const uint32_t lsw = (lane & 7) << 4, lhi = (lane >> 4) << 4, lrow = (lane & 15) * 128;
    const bool el = elect_one();
    if (el) {
      mbar_init(bar, 1); mbar_init(bar + 8, 1);
      asm volatile("fence.mbarrier_init.release.cluster;" ::: "memory");
    }
#pragma unroll 1
    for (int rd = 0; rd < (NLAYERS > 1 ? 5 : 2); rd++) {
      if (rd >= 2 && warp >= 8) break;
      const int tk = rd < 2 ? aux * 12 + warp : aux * 8 + warp;
      const int half = tk & 1;
      const int blk = rd < 2 ? (tk >> 1) * 2 + rd : (4 - rd) * 16 + (tk >> 1);
      const CUtensorMap* tm = rd < 2 ? &tm_wqA : (rd == 2 ? &tm_wqB : &tm_wf);
      const int j0 = (blk & 15) >> 1;
#define AUX_LOAD(n) { const uint32_t d_ = buf + ((n) & 1) * 8192, b_ = bar + ((n) & 1) * 8; const int r_ = kslice(j0, 2 * ((AUXORD >> (4 * (n))) & 7) + half) * 64; \
        mbar_expect_tx(b_, 8192); tma_load_2d(d_, tm, b_, blk * 64, r_); tma_load_2d(d_ + 4096, tm, b_, blk * 64, r_ + 32); }
      if (el) {
        if (rd == 3) { wait_flag(&g_flags.wfready[j0].v, ep1 * 16); fence_proxy_async_global(); }
        AUX_LOAD(0); AUX_LOAD(1);
      }
      __syncwarp();
      float cs[8][4];
#pragma unroll
      for (int i = 0; i < 8; i++) cs[i][0] = cs[i][1] = cs[i][2] = cs[i][3] = 0.f;
#pragma unroll 1
      for (int n = 0; n < 8; n++) {
        const uint32_t tb = buf + (n & 1) * 8192 + lrow;
        mbar_wait(bar + (n & 1) * 8, (n >> 1) & 1);
#pragma unroll
        for (int i = 0; i < 16; i++) {
          uint32_t b0, b1, b2, b3;
          ldsm_x4_t(tb + (i >> 2) * 2048 + (((i & 3) * 32 + lhi) ^ lsw), b0, b1, b2, b3);
          mma_bf16(cs[2 * (i & 3)], 0x3F803F80u, 0x3F803F80u, 0x3F803F80u, 0x3F803F80u, b0, b1);
          mma_bf16(cs[2 * (i & 3) + 1], 0x3F803F80u, 0x3F803F80u, 0x3F803F80u, 0x3F803F80u, b2, b3);
        }
        __syncwarp();
        if (el && n < 6) AUX_LOAD(n + 2);
        __syncwarp();
      }
      if (lane < 4) {
#pragma unroll
        for (int i = 0; i < 8; i++) st_b64(&g_colsum[rd >= 2][blk * 32 + i * 4 + lane][half], __float_as_uint(cs[i][0]), (__float_as_uint(cs[i][1]) & ~3u) | (ep1 & 3));
      }
      __syncwarp();
    }
  } else if (warp >= 8) {
    asm volatile("setmaxnreg.dec.sync.aligned.u32 40;");
    if (warp == 8) {
      const bool el = elect_one();
      cluster_wait();
      if (el) {
        if (PRL == 0) PROFT(445);
#pragma unroll 1
        for (int l = 0; l < NLAYERS; l++) {
          const uint32_t par = l & 1;
          const CUtensorMap* tqk = par ? &tm_wf : &tm_wqA;
          const CUtensorMap* tv = par ? &tm_wqB : &tm_wqA;
          const CUtensorMap* two = par ? &tm_woB : &tm_woA;
          if (l == 1) { LOAD_EPOCH(); wait_flag(&g_flags.wfready[jj].v, ep1 * 16); fence_proxy_async_global(); }
#pragma unroll 1
          for (int u = l ? 0 : EARLY; u < 32; u++) {
            const uint32_t fb = bar_full + u * 8;
            const int v = (l || u > 7) ? u : u - 4;
            const bool res = u < 11 || (u >= 18 && u < 22);
            mbar_expect_tx(fb, res ? QST : QST + SLOT);
            const int row = kslice(jj, v < 4 ? v & 1 : (u < 18 ? u - 2 : (u < 22 ? u - 6 : u - 20))) * 64 + (int)rank * 32;
            const int ps = v < 4 ? v >> 1 : (u >= 18), col = jj * 128 + ps * 64;
            const int c0 = par ? jj * 128 + (ps ? 0 : 1024) : col;
            const uint32_t dst = sbase + (u & 3) * QST + rank * 4096;
            uint32_t op[7] = {dst, dst + 8192, dst + 16384, (uint32_t)c0, (uint32_t)(c0 + (par ? 64 : 1024)), (uint32_t)(col + 2048), (uint32_t)row};
            PINU(op, 7);
            mbar_wait_sl(bar_done + (u >= 4 ? u - 4 : 43 + u + (u >> 1)) * 8, par ^ (u < 4));
            tma_load_2d_mc(op[0], tqk, fb, op[3], op[6]);
            tma_load_2d_mc(op[1], tqk, fb, op[4], op[6]);
            tma_load_2d_mc(op[2], tv, fb, op[5], op[6]);

            if (u < 8) PROFL3(472 + u);
          }
#pragma unroll 1
          for (int s = 0; s < 16; s++) {
            const uint32_t fb = bar_full + (32 + s) * 8;
            const int ts = s + 1;
            const bool ot = s >= 5 && ts < 8;
            mbar_expect_tx(fb, SLOT);
            uint32_t op[4] = {sbase + rank * 8192 + (uint32_t)((WO_BSLOT >> (4 * s)) & 15) * SLOT, (uint32_t)wslice(jj, s) * 64,
                              sbase + (uint32_t)((WO_ASLOT(par) >> (4 * ts)) & 15) * SLOT, (uint32_t)wslice(jj, ts) * 64};
            PINU(op, 4);
            mbar_wait_sl(bar_done + (28 + (uint32_t)((0xDCCBA98765433110ull >> (4 * s)) & 15)) * 8, par);
            tma_load_2d_mc(op[0], two, fb, jj * 128 + (int)rank * 64, op[1]);
            if (ot) {
              mbar_expect_tx(bar_chk - 8 + ts * 8, SLOT);
              tma_load_t(op[2], &tm_o, bar_chk - 8 + ts * 8, op[3], mm * 128);
            }
          }
        }
      }
      __syncwarp();
    } else if (warp == 9) {
      const bool el = elect_one();
      if (el) {
#pragma unroll
        for (int i = 0; i < 2; i++) {
          mbar_expect_tx(bar_full + 32 + i * 8, SLOT);
          mbar_wait_sl(bar_full + (i ? OWNW1 : OWNW0) * 8, 0);
          tma_load_t(sbase + OFF_S + i * SLOT, &tm_x0, bar_full + 32 + i * 8, jj * 128 + i * 64, mm * 128);
        }
      }
      __syncwarp();
      LOAD_EPOCH();
#pragma unroll 1
      for (int lp = 0; lp < 4 * NLAYERS; lp++) {
        const int l = lp >> 2, ph = lp & 3;
        if (ph == 3) continue;
        const uint32_t par = l & 1;
        const unsigned* pp = reinterpret_cast<const unsigned*>(g_obuf + (ph >> 1) * 64 + (size_t)(mm * 128 + (ph ? 0 : S_LEN) + ((lane & 7) | PROWS) * 16 + (jj & 1) * 8) * D_MODEL +
                                                               (jj >> 1) * 16 + srcb(jj, lane >> 3) * 128);
        const CUtensorMap* tm = lp ? &tm_o : &tm_x0;
        const int row = mm * 128 + ((ph || !l) ? 0 : S_LEN);
        const uint32_t bit = ph ? O_BIT(l) : X_BIT(l - 1);
        const uint32_t slots = ph ? (uint32_t)(WO_ASLOT(par) >> (ph * 32 - 28)) : 0x8769876u;
        const unsigned long long fr = ph == 0 ? XPACE : ph == 1 ? (par ? FRB : 0x35351F1E1Dull) : 0x27262524232232ull;
        uint32_t no = (lp == 0 || (lp & 7) == 1) ? 0 : (ph == 1 ? NOB : (ph ? NO1 : NOX)), v0 = 0, v1 = 0;
        mbar_wait_sl(ph ? bar_done + ((uint32_t)fr & 63) * 8 : (l ? bar_done + 47 * 8 : bar_full), ph ? par : (l ? par ^ 1 : 0));
        if (el && ph) PROFT(324 + l * 16 + ph);
        __syncwarp();
        if (no && (ph == 1 ? SPD1 : (ph ? SPD2 : SPD0))) __nanosleep(ph == 1 ? SPD1 : (ph ? SPD2 : SPD0));
        if (no) { v0 = ld_relaxed(pp); if (ph != 1) __nanosleep(POLLGAP); v1 = ld_relaxed(pp); }
#pragma unroll 1
        for (int i = lp ? 0 : 4; i < (ph == 1 ? 5 : 7); i++, no >>= 8) {
          uint32_t op[4] = {(lp ? bar_chk + (ph >> 1) * 112 : bar_full + 32) + i * 8  , sbase + ((slots >> (4 * i)) & 15) * SLOT,
                            (uint32_t)(srcb(jj, i) * 128 + (ph >> 1) * 64), bar_done + ((uint32_t)(fr >> (8 * i)) & 63) * 8};
          PINU(op, 4);
          if (el) mbar_expect_tx(op[0], SLOT);
#pragma unroll 1
          for (int it = 0; (no & 0xFF) && it < (1 << 18); it++) {
            no &= __ballot_sync(0xffffffffu, (v0 ^ bit) & 1) >> (8 * i);
            if (no) v0 = ld_relaxed(pp);
            if (!(no & 0xFF)) break;
            no &= __ballot_sync(0xffffffffu, (v1 ^ bit) & 1) >> (8 * i);
            if (no) v1 = ld_relaxed(pp);
          }
          if (i >= (ph ? 1 : 4)) mbar_wait_sl(op[3], par);
          if (el) {
            if (i == 0) PROFT(320 + l * 16 + ph);
            PROFL3(448 + ph * 8 + i);
            tma_load_t(op[1], tm, op[0], op[2], row);
          }
          __syncwarp();
        }
        if (ph == 0 && el) {
          if (l) { wait_flag(&g_flags.xready[l][mm].v, ep1 * 8); fence_proxy_async_global(); }
#pragma unroll 1
          for (int u = 11; u < 34; u++) {
            if (u == 18) u = 22;
            if (u == 32) mbar_expect_tx(bar_xr, 2 * SLOT);
            uint32_t op[3] = {sbase + OFF_RA + (u & 3) * SLOT, u < 32 ? bar_full + u * 8 : bar_xr, (uint32_t)kslice(jj, u < 18 ? u - 2 : (u < 32 ? u - 20 : u - 32)) * 64};
            PINU(op, 3);
            mbar_wait_sl(bar_done + (u - 4) * 8, par);
            tma_load_t(op[0], tm, op[1], op[2], row);
          }
        }
        __syncwarp();
      }
      if (el && atomicAdd(&g_flags.done.v, 1) == ep1 * NMAIN - 1) asm volatile("st.relaxed.gpu.global.u32 [%0], %1;" :: "l"(&g_flags.epoch.v), "r"(ep1) : "memory");
      __syncwarp();
      cluster_wait();
    } else {
      const int hw = warp - 10;
      if (elect_one()) {
        const uint32_t fb = bar_full + 16 + hw * 8;
        mbar_expect_tx(fb, QST + SLOT);
#pragma unroll
        for (int i = 0; i < 6; i++) tma_load_2d(sbase + (2 + hw) * QST + i * 4096, &tm_wqA, fb, jj * 128 + (i >> 1) * 1024, srcb(jj, 2 + hw) * 128 + (i & 1) * 32);
        tma_load_t(sbase + OFF_RA + (2 + hw) * SLOT, &tm_x0, fb, srcb(jj, 2 + hw) * 128, mm * 128);
        mbar_arrive_local(fb + 32);
        if (PRL == 0) PROFT(446 + hw);
      }
      __syncwarp();
      const unsigned epoch = hw ? __shfl_sync(0xffffffffu, epoch0, 31) : ld_relaxed(prm.epoch), ep1 = epoch + 1;
      const bool el = elect_one();
      cluster_wait();
      if (hw == 0) {
        mbar_wait_sl(bar_full + 8, 0);
        if (lane < 7) prefetch_tmap(lane == 0 ? &tm_os : lane == 1 ? &tm_o : lane == 2 ? &tm_wf : lane == 3 ? &tm_wqB : lane == 4 ? &tm_woA : lane == 5 ? &tm_woB : &tm_phi);
#pragma unroll 1
        for (int i = 0; i < (NLAYERS > 1 ? 5 : 0); i++) {
          if (i == 0) mbar_wait_sl(bar_done + FD0 * 8, 0);
          if (el) {
            if (i == 0) { mbar_expect_tx(bar_phi, 2 * SLOT + 8192); tma_load_2d(sbase + OFF_PHI, &tm_phi, bar_phi, 0, jj * 128); }
            else tma_load_2d(sbase + 12 * SLOT - 4096 + i * 4096, &tm_wqB, bar_phi, jj * 128 + ((i - 1) >> 1) * 64, mm * 64 + (~i & 1) * 32);
          }
          __syncwarp();
          __nanosleep(PFGAP);
        }
      } else {
        if (lane < 24) {
          const uint32_t one = (lane & 8) ? 0u : 0x3F80u << ((lane & 1) * 16), w = (lane >> 1) & 3;
          sts128(sbase + OFF_ID + lane * 16, w == 0 ? one : 0u, w == 1 ? one : 0u, w == 2 ? one : 0u, w == 3 ? one : 0u);
        }
#pragma unroll 1
        for (int b = 0; b < 2; b++) {
          float4* z = reinterpret_cast<float4*>(g_kv[b] + (jj * 4) * KVH + mm * (4 * KVH / 16)) + lane;
#pragma unroll
          for (int i = 0; i < 6; i++) z[i * 32] = make_float4(0.f, 0.f, 0.f, 0.f);
        }
#pragma unroll 1
        for (int i = 0; i < 16; i++) {
          const int b = i >> 2;
          const uint32_t v = (b == 0 ? O_BIT(0) : b == 1 ? X_BIT(0) : H_BIT(0)) + 1;
          uint4* p = b < 2 ? reinterpret_cast<uint4*>(g_obuf + (size_t)(b * S_LEN + mm * 128 + (i & 3) * 32 + (lane >> 3) * 8) * D_MODEL + jj * 128 + (b ? 0 : 64)) + (lane & 7)
                           : g_halo + (size_t)(mm * 8 + jj) * 512 + i * 32 + lane;
          *p = make_uint4(v, v, v, v);
        }
        fence_proxy_async_global();
      }
      __syncwarp();
      uint32_t chkp = 0;
#pragma unroll 1
      for (int lp = 0; lp < 8 * NLAYERS; lp++) {
        const int l = lp >> 3, tk = lp & 7, ph = tk ? 2 - hw : 0;
        const uint32_t par = l & 1;
        int lane; asm volatile("mov.u32 %0, %%laneid;" : "=r"(lane));
        if (tk == 5 || (hw && tk == 0 && l)) {
          const uint32_t bit = ph ? O_BIT(l) : X_BIT(l - 1);
          uint32_t slots = ph ? (uint32_t)(WO_ASLOT(par) >> (ph * 32 - 28)) : 0x8769876u;
          const uint32_t a0 = sbase + (lane & 7) * 126 + lane * 4 + (lane & 1) * 14;
#pragma unroll 1
          for (int c = 0; c < 7; c++, slots >>= 4) {
            const uint32_t cb = bar_chk + 112 - hw * 112 + c * 8;
#pragma unroll 1
            for (int it = 0; it < (1 << 12); it++) {
              mbar_wait_sl(cb, (chkp >> c) & 1);
              chkp ^= 1u << c;
              if (el) PROFL3(384 + ph * 8 + c);
              uint32_t bad;
              asm volatile("{\n.reg .b32 w<16>;\n"
                           "ld.shared.u32 w0, [%1 + 0];\n"
                           "ld.shared.u32 w1, [%1 + 1024];\n"
                           "ld.shared.u32 w2, [%1 + 2048];\n"
                           "ld.shared.u32 w3, [%1 + 3072];\n"
                           "ld.shared.u32 w4, [%1 + 4096];\n"
                           "ld.shared.u32 w5, [%1 + 5120];\n"
                           "ld.shared.u32 w6, [%1 + 6144];\n"
                           "ld.shared.u32 w7, [%1 + 7168];\n"
                           "ld.shared.u32 w8, [%1 + 8192];\n"
                           "ld.shared.u32 w9, [%1 + 9216];\n"
                           "ld.shared.u32 w10, [%1 + 10240];\n"
                           "ld.shared.u32 w11, [%1 + 11264];\n"
                           "ld.shared.u32 w12, [%1 + 12288];\n"
                           "ld.shared.u32 w13, [%1 + 13312];\n"
                           "ld.shared.u32 w14, [%1 + 14336];\n"
                           "ld.shared.u32 w15, [%1 + 15360];\n"
                           "lop3.b32 w0, w0, w1, %2, 0x7E;\n"
                           "lop3.b32 w2, w2, w3, %2, 0x7E;\n"
                           "lop3.b32 w4, w4, w5, %2, 0x7E;\n"
                           "lop3.b32 w6, w6, w7, %2, 0x7E;\n"
                           "lop3.b32 w8, w8, w9, %2, 0x7E;\n"
                           "lop3.b32 w10, w10, w11, %2, 0x7E;\n"
                           "lop3.b32 w12, w12, w13, %2, 0x7E;\n"
                           "lop3.b32 w14, w14, w15, %2, 0x7E;\n"
                           "lop3.b32 w0, w0, w2, w4, 0xFE;\nlop3.b32 w6, w6, w8, w10, 0xFE;\nlop3.b32 w0, w0, w12, w14, 0xFE;\nlop3.b32 %0, w0, w6, 1, 0xA8;\n}\n"
                           : "=r"(bad) : "r"(a0 + (slots & 15) * SLOT), "r"(bit) : "memory");
              if (__all_sync(0xffffffffu, bad == 0)) break;
              if (el) {
                fence_proxy_async_smem();
                mbar_expect_tx(cb, SLOT);
                tma_load_t(sbase + (slots & 15) * SLOT, &tm_o, cb, srcb(jj, c) * 128 + (ph >> 1) * 64, mm * 128 + (ph ? 0 : S_LEN));
                RETRY_COUNT();
              }
              __syncwarp();
            }
            if (el) { mbar_arrive_local(bar_full + (c + (ph ? 25 + ph * 8 : 4)) * 8); PROFL3(416 + ph * 8 + c); PROF2V(); }
            __syncwarp();
          }
        } else if (hw && (tk & 5) == 1) {
          {
            const int hp = tk >> 1;
            const uint4* src = reinterpret_cast<const uint4*>(g_colsum[par][jj * 64 + hp * 32 + lane]);
            uint32_t bad;
            int it = 0;
            float c[6];
            do {
              bad = 0;
#pragma unroll
              for (int p = 0; p < 3; p++) {
                const uint4 v = ld_ll(src + ((par && p < 2) ? (hp ? -32 : 512) + p * 32 : p * 512));
                bad |= (v.y ^ ep1) | (v.w ^ ep1);
                c[2 * p] = __uint_as_float(v.x) + __uint_as_float(v.z); c[2 * p + 1] = __uint_as_float(v.y) + __uint_as_float(v.w);
              }
              bad &= 3;
              if (bad) __nanosleep(CSGAP);
            } while (bad && ++it < (1 << 16));
#pragma unroll
            for (int p = 0; p < 6; p++) {
              uint32_t h, m, lo;
              split3(c[p], h, m, lo);
              sts128(sbase + OFF_LNB + hp * 4096 + (p >> 1) * 1024 + lane * 32 + (p & 1) * 16, h | (m << 16), h | (lo << 16), h | (m << 16), lo | (m << 16));
            }
            fence_proxy_async_smem();
            __syncwarp();
            if (el) { mbar_arrive_local(hp ? bar_stat2 : bar_stat); if (hp == 0) PROFT(324 + l * 16); }
            __syncwarp();
          }
        } else if (tk == 0) {
          mbar_wait_sl(bar_done + (l ? 24 : 56), par);
          const uint4* sp = reinterpret_cast<const uint4*>(g_stats + (size_t)(mm * 128) * 8) + lane;
          if (el) PROFL3(484);
#pragma unroll 1
          for (int hf = 2 * hw; hf < (l ? 4 : 2 + 2 * hw); hf++) {
            if (NLAYERS > 1 && l == 0 && el) tma_load_2d(sbase + 11 * SLOT + hf * 4096, &tm_wqB, bar_phi, 1024 + jj * 128 + (hf >> 1) * 64, mm * 64 + (hf & 1) * 32);
            __syncwarp();
            uint4 v[4];
            uint32_t bad;
            int it = 0;
            do {
              bad = 0;
#pragma unroll
              for (int i = 0; i < 4; i++) { v[i] = ld_ll(sp + (hf * 4 + i) * 32); bad |= (v[i].y ^ STAT_TAG(l)) | (v[i].w ^ STAT_TAG(l)); }
              bad &= 3;
              if (bad) __nanosleep(200);
            } while (bad && ++it < (1 << 16));
            __syncwarp();
            if (el) PROFL3(480 + hf);
            float mean = 0.f, m2 = 0.f;
#pragma unroll
            for (int i = 0; i < 4; i++) {
              float a = __uint_as_float(v[i].x) + __uint_as_float(v[i].z);
              a += __shfl_xor_sync(0xffffffffu, a, 1); a += __shfl_xor_sync(0xffffffffu, a, 2);
              a *= 0.125f;
              const float e0 = __uint_as_float(v[i].x) - a, e1 = __uint_as_float(v[i].z) - a;
              float q = fmaf(fmaf(e0, e0, e1 * e1), 128.f, __uint_as_float(v[i].y) + __uint_as_float(v[i].w));
              q += __shfl_xor_sync(0xffffffffu, q, 1); q += __shfl_xor_sync(0xffffffffu, q, 2);
              if ((lane & 3) == i) { mean = a; m2 = q; }
            }
            const uint32_t row = hf * 32 + (lane & 3) * 8 + (lane >> 2);
            uint32_t h, m, lo;
            split3(-0.5f * mean, h, m, lo);
            sts128(sbase + OFF_LNA + row * 16, h | (h << 16), m | (h << 16), lo | (m << 16), m | (lo << 16));
            sts32f(sbase + OFF_ST + row * 4, rsqrtf(m2 * (1.f / 1024.f) + 1e-5f));
          }
          if (hw) continue;
          fence_proxy_async_smem();
          __syncwarp();
          if (el) { mbar_arrive_local(bar_stat); PROFT(323 + l * 16); }
          __syncwarp();
#pragma unroll 1
          for (int i = 0; i < 8 - 4 * l; i++) {
            asm volatile("prefetch.global.L2 [%0];" :: "l"(i < 4 ? (l ? prm.wB_o : prm.wA_o) + (size_t)cta * 8192 + i * 2048 + lane * 64
                                                                 : prm.wB_qkv + (size_t)(cta * 8 + (i - 4) * 2 + (lane >> 4)) * 3072 + 2048 + (lane & 15) * 64));
            __nanosleep(PFGAP);
          }
        } else if (lp == 3) {
#pragma unroll 1
          for (int c = 0; c < (NLAYERS > 1 ? 8 : 0); c++) {
            if (!(c & 3)) { asm volatile("bar.sync %0, 288;" :: "r"(BAR_WF + (c >> 2)) : "memory"); fence_proxy_async_smem(); }
            if (el) {
              tma_store_2d(&tm_wf, sbase + 11 * SLOT + c * 4096, (c < 4 ? 1024 : -128) + jj * 128 + (c >> 1) * 64, mm * 64 + (c & 1) * 32);
              if (c == 7) {
                asm volatile("cp.async.bulk.commit_group;\ncp.async.bulk.wait_group.read 0;" ::: "memory");
                mbar_arrive_local(bar_phi + 8);
              } else __nanosleep(WFGAP);
            }
            __syncwarp();
          }
          if (el) { bulk_commit_wait(); signal_release(&g_flags.wfready[jj].v); PROFT(335); }
          __syncwarp();
        } else if (tk == 2 || tk == 4) {
          if (par) continue;
          const int i = tk >> 2;
          mbar_wait_sl(bar_done + (i ? HW1 : (hw ? 19 : HW0)) * 8, 0);
          const uint4* src = g_halo + (size_t)(mm * 8 + jj - 8) * 512 + i * 256 + hw * 128 + lane;
          uint4 v[4];
          int it = 0;
          bool ok;
          do {
#pragma unroll
            for (int j = 0; j < 4; j++) v[j] = mm ? ld_b128(src + j * 32) : make_uint4(H_BIT(l), 0, 0, 0);
            ok = __all_sync(0xffffffffu, (((v[0].x ^ H_BIT(l)) | (v[1].x ^ H_BIT(l)) | (v[2].x ^ H_BIT(l)) | (v[3].x ^ H_BIT(l))) & 1) == 0);
          } while (!ok && ++it < (1 << 16));
#pragma unroll
          for (int j = 0; j < 4; j++) sts128(sbase + OFF_S + hw * 8192 + j * 512 + lane * 16, v[j].x, v[j].y, v[j].z, v[j].w);
          __syncwarp();
          if (el) { mbar_arrive_local(bar_halo + hw * 8); PROFT(331 + l * 16 + i * 2 + hw); }
          __syncwarp();
        } else if (tk == 6 && hw == 0 && l < NLAYERS - 1) {
          bar_sync<BAR_X1, 288>();
          if (el) {
            PROFT(328 + l * 16);
            mbar_wait_sl(bar_full + XD * 8, par ^ 1);
            tma_store_t(&tm_o, sbase + 11 * SLOT, jj * 128 + 64, mm * 128 + S_LEN);
            bulk_commit_wait();
            signal_release(&g_flags.xready[l + 1][mm].v);
            PROFT(330 + l * 16);
          }
          __syncwarp();
        }
      }
    }
    cluster_sync();
  } else {
    asm volatile("setmaxnreg.inc.sync.aligned.u32 232;");
    const int wg = warp >> 2;
    const int r0 = warp * 16;
    const uint32_t pK = sbase + OFF_S, pV = sbase + OFF_S + SLOT;
#define PMASKS(on, bit) const uint32_t pm0 = ((on) && t == (g >> 1)), pbit = (bit)
#define PBIT(w) (((w) & ~pm0) | (pbit & pm0))
#define LANE_CONSTS() \
    int lane; asm volatile("mov.u32 %0, %%laneid;" : "=r"(lane)); \
    const int g = lane >> 2, t = lane & 3; \
    const uint32_t srowoff = (r0 + (lane & 15)) * 128, lsw = (lane & 7) << 4, lhi = (lane >> 4) << 4, lsw2 = (lane & 6) << 3; \
    (void)g; (void)t; (void)srowoff; (void)lsw; (void)lhi; (void)lsw2;
    uint32_t stgp = 0, peer;
    asm volatile("mapa.shared::cluster.u32 %0, %1, %2;" : "=r"(peer) : "r"(sbase), "r"(rank ^ 1));
    peer -= sbase;
    const uint32_t dA0 = (((sbase & 0x3FFFF) + wg * 8192) >> 4) | 0x10000u, dB0 = ((sbase & 0x3FFFF) >> 4) | 0x2000000u;
#define DESC(lo, hi) ((uint64_t)(uint32_t)(lo) | ((uint64_t)(hi) << 32))
#define STG_ARRIVE() { __syncwarp(); if (elect_one()) mbar_arrive_local(bar_stg); }
#define STG_WAIT() { mbar_wait(bar_stg, stgp); stgp ^= 1; }
#define PROFS() do {} while (0)
#define REL(addr) { if (elect_one()) { mbar_arrive_local(addr); asm volatile("mbarrier.arrive.shared::cluster.b64 _, [%0];" :: "r"((addr) + peer) : "memory"); } }
#define QSTEP(ACC, DA, SC) { \
      const uint32_t da = (DA), db = dB0 + (ub & 0x18) * (QST >> 7); \
      mbar_wait(ub, par); \
      wgmma_fence(); \
      wgmma4_n192<SC>(ACC, da, db); \
      wgmma_commit(); PROFS(); }
#define QREL() { wgmma_wait<1>(); REL(ub + 376); ub += 8; }
#define RA_CUR (dA0 + (OFF_RA >> 4) + (ub & 0x18) * (SLOT >> 7))
#define PUMP1() { QSTEP(S1, RA_CUR, 1); QREL(); }
#define PUMPN() { wgmma_fence(); wgmma4_n192<1>(S1, RA_CUR, dB0 + (ub & 0x18) * (QST >> 7)); wgmma_commit(); PROFS(); QREL(); }
#define PUMP0() { PUMP1(); SCHED_FENCE(); }
#define WSTEP() { \
      const uint32_t s4 = (ub - bar_full - 256) >> 1; \
      const uint32_t da = dA0 + (((uint32_t)(WO_ASLOT(par) >> s4) & 15) << 10), db = dB0 + (((uint32_t)(WO_BSLOT >> s4) & 15) << 10); \
      mbar_wait(ub, par); \
      wgmma_fence(); \
      wgmma4_n128<1>(S1, da, db); \
      wgmma_commit(); PROFS(); \
      wgmma_wait<1>(); \
      if (s4) REL(ub + 376); \
      ub += 8; }
#define PUMPS(n) { _Pragma("unroll 1") for (int i_ = 0; i_ < (n); i_++) PUMP1(); }
#define LNSTEP(ACC, hh) { wgmma_fence(); wgmma_n192<1, 0>(ACC, make_desc(sbase + OFF_LNA + wg * 1024, 0, 128) ^ (1ull << 62), make_desc(sbase + OFF_LNB + (hh) * 4096, 0, 128) ^ (1ull << 62)); }
#define WARP_STORE(tm, tile, col, row) { fence_proxy_async_smem(); __syncwarp(); WARP_STORE0(tm, tile, col, row); }
#define WARP_STORE0(tm, tile, col, row) { \
      if (elect_one()) { tma_store_2d(tm, (tile) + r0 * 128, col, (row) + r0); asm volatile("cp.async.bulk.commit_group;" ::: "memory"); } __syncwarp(); }
#define TILE_CONSTS(base, on, bit) \
      uint32_t ta[5]; \
      { PMASKS(on, bit); (void)pbit; ta[4] = pm0; } \
      _Pragma("unroll") for (int j = 0; j < 4; j++) ta[j] = (base) + srowoff + ((((uint32_t)j << 5) + lhi) ^ lsw); \
      PINU(ta, 5); SCHED_FENCE(); \
      const uint32_t pm0 = ta[4], pbit = (bit)
#define X_OUT(pc, W) { \
      _Pragma("unroll") for (int j = 0; j < 4; j++) \
        stsm_x4(ta[j] + (pc) * SLOT, \
                PBIT(pack_bf16((W)[j * 8 + 0], (W)[j * 8 + 1])), PBIT(pack_bf16((W)[j * 8 + 2], (W)[j * 8 + 3])), \
                (pack_bf16((W)[j * 8 + 4], (W)[j * 8 + 5])), (pack_bf16((W)[j * 8 + 6], (W)[j * 8 + 7]))); }
#define REST_P1(SKEW) { \
      mbar_wait(bar_stat2, par); \
      LNSTEP(S1, 1); \
      wgmma_commit(); \
      _Pragma("unroll 1") while (ub < bar_full + 256) { \
        const bool hold = ub == bar_full + 256 - 8 * (SKEW) && wg == 0; \
        if (hold) { wgmma_wait<0>(); REL(ub + 376); bar_sync<BAR_SKEW, 256>(); } \
        QSTEP(S1, RA_CUR, 1); \
        if (ub == bar_full + 248 && wg == 1) bar_arrive<BAR_SKEW, 256>(); \
        wgmma_wait<1>(); if (!hold) REL(ub + 376); ub += 8; \
      } \
      mbar_wait(bar_done + (31 - (SKEW)) * 8, par);        \
      wgmma_wait<0>(); \
      ACC_FENCE(S1, 96); \
      REL(bar_done + 31 * 8); \
      PROF(13); }
#define FOLD(tile, rd) { \
          LANE_CONSTS(); \
          float d[32]; \
          ACC_DEF(d, 32); \
          mbar_wait(bar_phi, 0); \
          wgmma_fence(); \
          _Pragma("unroll") for (int i = 0; i < 2; i++) { \
            const uint64_t da = make_desc((tile) + wg * 8192 + i * 64, 16, 1024); \
            const uint64_t db = make_desc(sbase + OFF_PHI + wg * 4096 + i * 2048, 16, 512) ^ (3ull << 62); \
            wgmma_n32<0>(d + i * 16, da, db); wgmma_n32<1>(d + i * 16, da + 2, db + 64); \
          } \
          wgmma_commit(); \
          PUMP0(); \
          ACC_FENCE(d, 32); \
          bar_wg(wg); \
          _Pragma("unroll") for (int i = 0; i < 4; i++) { \
            const float* x = d + (i & 1) * 8 + (i >> 1) * 2; \
            if (rd) sts128((tile) + wg * 8192 + ((warp & 3) * 16 + (i >> 1) * 8 + g) * 128 + (((2 * t + (i & 1)) ^ g) << 4), \
                           pack_bf16(x[0], x[1]), pack_bf16(x[4], x[5]), pack_bf16(x[16], x[17]), pack_bf16(x[20], x[21])); \
            else stsm_x4((tile) + srowoff + ((((uint32_t)i << 5) + lhi) ^ lsw), pack_bf16(d[i * 8], d[i * 8 + 1]), pack_bf16(d[i * 8 + 2], d[i * 8 + 3]), \
                         pack_bf16(d[i * 8 + 4], d[i * 8 + 5]), pack_bf16(d[i * 8 + 6], d[i * 8 + 7])); \
          } \
          }
#define XM_ISSUE() { mbar_wait(bar_xr, par); wgmma_fence(); \
      wgmma_copy(T_, dA0 + (OFF_RA >> 4), make_desc(sbase + OFF_ID, 128, 128) ^ (1ull << 62)); }
#define COPYN(d, s, n) _Pragma("unroll") for (int i_ = 0; i_ < (n); i_++) { uint32_t c_; asm volatile("mov.b32 %0, %1;" : "=r"(c_) : "f"((s)[i_])); (d)[i_] = __uint_as_float(c_); }
#define COPY64(d, s) COPYN(d, s, 64)
#define XM_DONE() { ACC_FENCE(T_, 64); COPY64(S1, T_); ACC_FENCE(S1, 64); \
      __syncwarp(); if (elect_one()) mbar_arrive_local(bar_lx); }
#define LOAD_X() { float T_[64]; ACC_DEF(T_, 64); wgmma_wait<0>(); XM_ISSUE(); wgmma_commit(); wgmma_wait<0>(); XM_DONE(); }

    float S0[96], S1[96];
    if (lane == 0) epoch0 = ld_relaxed(prm.epoch);
    __syncwarp();
    uint32_t ub = bar_full;
    {
      constexpr int l = 0;
      constexpr uint32_t par = 0;
      (void)l;
      ACC_DEF(S0, 96);
      QSTEP(S0, RA_CUR, 0);
      PROF(0);
      SCHED_FENCE();
      cluster_wait();
      ub += 8;
#pragma unroll 1
      for (int i = 1; i < 5; i++) {
        QSTEP(S0, dA0 + (OFF_RA >> 4) + i * (SLOT >> 4), 1);
        QREL();
      }
    }
    const unsigned epoch = __shfl_sync(0xffffffffu, epoch0, 0), ep1 = epoch + 1;
#pragma unroll 1
    for (int l = 0;; l++) {
      const uint32_t par = l & 1;
      PROF(1);
      {
        LANE_CONSTS();
        uint32_t ta[4];
#pragma unroll
        for (int j = 0; j < 4; j++) ta[j] = pK + srowoff + ((((uint32_t)j << 5) + lhi) ^ lsw);
        float p0, p1, a0 = 0.f, a1 = 0.f, q0 = 0.f, q1 = 0.f;
#define STATS(j0, j1) _Pragma("unroll") for (int j = (j0); j < (j1); j++) { \
          uint32_t x[4]; \
          ldsm_x4(ta[j & 3] + (j >> 2) * SLOT, x[0], x[1], x[2], x[3]); \
          if (j == 0) { p0 = __shfl_sync(0xffffffffu, bf_lo(x[0]), lane & 28); p1 = __shfl_sync(0xffffffffu, bf_lo(x[1]), lane & 28); } \
          _Pragma("unroll") for (int i = 0; i < 4; i += 2) { \
            const float d0 = bf_lo(x[i]) - p0, d1 = bf_hi(x[i]) - p0, d2 = bf_lo(x[i + 1]) - p1, d3 = bf_hi(x[i + 1]) - p1; \
            a0 += d0 + d1; a1 += d2 + d3; \
            q0 = fmaf(d1, d1, fmaf(d0, d0, q0)); q1 = fmaf(d3, d3, fmaf(d2, d2, q1)); } } \
          asm volatile("" : "+f"(a0), "+f"(a1), "+f"(q0), "+f"(q1), "+f"(p0), "+f"(p1)); SCHED_FENCE()
        if (SB0) { STATS(0, SB0); }
        bar_wg(wg);
        QSTEP(S0, dA0 + ((OFF_S + SLOT) >> 4), 1);
        QREL();
        SCHED_FENCE();
        STATS(SB0, SB1);
        ACC_DEF(S1, 96);
        QSTEP(S1, dA0 + (OFF_S >> 4), 0);
        QREL();
        SCHED_FENCE();
        STATS(SB1, SB2);
        QSTEP(S1, dA0 + ((OFF_S + SLOT) >> 4), 1);
        QREL();
        SCHED_FENCE();
        STATS(SB2, 8);
#pragma unroll
        for (int o = 1; o <= 2; o <<= 1) {
          a0 += __shfl_xor_sync(0xffffffffu, a0, o); a1 += __shfl_xor_sync(0xffffffffu, a1, o);
          q0 += __shfl_xor_sync(0xffffffffu, q0, o); q1 += __shfl_xor_sync(0xffffffffu, q1, o);
        }
        if (t == 1) { a0 = a1; q0 = q1; p0 = p1; }
        if (t < 2) st_b64(g_stats + (size_t)(mm * 128 + r0 + g + t * 8) * 8 + jj, __float_as_uint(fmaf(a0, 1.f / 128.f, p0)),
                          (__float_as_uint(fmaxf(fmaf(a0 * (-1.f / 128.f), a0, q0), 0.f)) & ~3u) | STAT_TAG(l));
        if (l) { asm volatile("cp.async.bulk.wait_group 0;" ::: "memory"); bar_arrive<BAR_X1, 288>(); }
#pragma unroll 1
        while (ub < bar_full + 144) {
          QSTEP(S0, RA_CUR, 1);
          if (ub == bar_full + 64) PROF(2);
          QREL();
        }
      }
      LANE_CONSTS();
      mbar_wait(bar_stat, par);
      LNSTEP(S0, 0);
      wgmma_commit();
      const float rs0 = lds32f(sbase + OFF_ST + (r0 + g) * 4), rs1 = lds32f(sbase + OFF_ST + (r0 + g + 8) * 4);
      PUMP0();
      ACC_FENCE(S0, 96);
      PROF(3);
      if (!par) {
        constexpr uint32_t par = 0;
        uint32_t qa[16];
        uint32_t kf[24], vf[24];
#define DRAIN_A(ACC, hp, PMP) { \
          LANE_CONSTS(); \
          FRAG(kf, ACC + 32, 0, (hp) * 2); \
          PMP; \
          FRAG(vf, ACC + 64, 1, (hp) * 2 + 1); \
          _Pragma("unroll") for (int i_ = 0; i_ < 16; i_++) qa[i_] = pack_bf16(ACC[2 * i_], ACC[2 * i_ + 1]); \
          PINU(qa, 16); }
        DRAIN_A(S0, 0, PUMP0());
        if (l == 0 && NLAYERS > 1) {
#pragma unroll 1
          for (int rd = 1; rd >= 0; rd--) {
            FOLD(sbase + (12 - rd) * SLOT, rd);
            asm volatile("bar.arrive %0, 288;" :: "r"(BAR_WF + 1 - rd) : "memory");
          }
        }
        PUMPS(FPUMP);
#pragma unroll 1
        for (int h = 0; h < 2; h++) {
          PROFH(4, 16);
          LANE_CONSTS();
          FRAG_PUT(kf + 16, 0); FRAG_PUT(vf + 16, 1);
          STG_ARRIVE();
          if (h) { PROF(8); LOAD_X(); PROF(9); WSTEP(); PROF(10); } else PUMPS(HPUMP2);
          const bool gt0 = 2 * t > g, gt1 = 2 * t >= g;
          uint32_t msk[2] = {(gt0 ? 0xFFFFu : 0u) | (gt1 ? 0xFFFF0000u : 0u), g == 2 * t ? 0x10001u : 0u};
          PINU(msk, 2);
          TILE_CONSTS(sbase, false, 0);
          (void)pm0; (void)pbit;
          if (h) PROF(12);
          STG_WAIT();
          if (h) PROF(14);
          if (warp < 2) mbar_wait(bar_halo, h);
          if (h) PROF(15);
          if (h == 0) mbar_wait(ub, par);
          FRAG_GET(kf, 0);
          PROFH(5, 17);
          float s[2][3][4];
#pragma unroll
          for (int ks = 0; ks < 2; ks++)
#pragma unroll
            for (int i = 0; i < 6; i++) {
              const int hh = i & 1, jb = 2 - (i >> 1);
              const uint32_t* b = kf + jb * 8 + hh * 4 + ks * 2;
              if (ks) mma_bf16(s[hh][jb], qa[hh * 8 + 4], qa[hh * 8 + 5], qa[hh * 8 + 6], qa[hh * 8 + 7], b[0], b[1]);
              else mma_bf16_z(s[hh][jb], qa[hh * 8], qa[hh * 8 + 1], qa[hh * 8 + 2], qa[hh * 8 + 3], b[0], b[1]);
            }
          if (h == 0) PUMPN()
          PROFH(6, 18);
          float va[2][2], vb[2][2], mx[2][2];
#pragma unroll
          for (int hh = 0; hh < 2; hh++) {
            va[hh][0] = gt0 ? s[hh][0][0] : s[hh][1][0];
            vb[hh][0] = gt1 ? s[hh][0][1] : s[hh][1][1];
            va[hh][1] = gt0 ? s[hh][1][2] : s[hh][2][2];
            vb[hh][1] = gt1 ? s[hh][1][3] : s[hh][2][3];
          }
          if (warp < 2 && mm == 0) {
#pragma unroll
            for (int hh = 0; hh < 2; hh++) { if (gt0) va[hh][0] = -INFINITY; if (gt1) vb[hh][0] = -INFINITY; }
          }
#pragma unroll
          for (int i = 0; i < 4; i++) mx[i >> 1][i & 1] = fmaxf(va[i >> 1][i & 1], vb[i >> 1][i & 1]);
#pragma unroll
          for (int o = 1; o <= 2; o <<= 1)
#pragma unroll
            for (int i = 0; i < 4; i++) mx[i >> 1][i & 1] = fmaxf(mx[i >> 1][i & 1], __shfl_xor_sync(0xffffffffu, mx[i >> 1][i & 1], o));
          const float sc0 = rs0 * (0.17677669529663687f * LOG2E), sc1 = rs1 * (0.17677669529663687f * LOG2E);
#pragma unroll
          for (int i = 0; i < 4; i++) {
            const float sc = (i & 1) ? sc1 : sc0, m = mx[i >> 1][i & 1];
            va[i >> 1][i & 1] = ex2((va[i >> 1][i & 1] - m) * sc); vb[i >> 1][i & 1] = ex2((vb[i >> 1][i & 1] - m) * sc);
            mx[i >> 1][i & 1] = va[i >> 1][i & 1] + vb[i >> 1][i & 1];
          }
          if (h == 0) { PIN(&va[0][0], 4); PIN(&vb[0][0], 4); PIN(&mx[0][0], 4); PUMP1(); }
          if (h) PROF(20);
          if (warp < 2) mbar_wait(bar_halo + 8, h);
          if (h) PROF(21);
          if (h == 0) mbar_wait(ub, par);
          FRAG_GET(vf, 1);
#pragma unroll
          for (int o = 1; o <= 2; o <<= 1)
#pragma unroll
            for (int i = 0; i < 4; i++) mx[i >> 1][i & 1] += __shfl_xor_sync(0xffffffffu, mx[i >> 1][i & 1], o);
          float o[8][4];
          uint32_t pa[4][2];
#pragma unroll
          for (int i = 0; i < 4; i++) {
            const float iv = rcp_fast(mx[i >> 1][i & 1]);
            const uint32_t w = pack_bf16(va[i >> 1][i & 1] * iv, vb[i >> 1][i & 1] * iv);
            pa[i][0] = w & msk[0]; pa[i][1] = w & ~msk[0];
          }
          PROFH(7, 19);
#pragma unroll
          for (int i = 7; i >= 0; i--) {
            const uint32_t* a = vf + (i >> 2) * 8 + (i & 3) * 2;
            mma_bf16_z(o[i], a[0], a[1], a[8], a[9], pa[(i & 2) + (i >> 2)][0], pa[(i & 2) + (i >> 2)][1]);
          }
          if (h == 0) PUMPN() else mbar_wait(bar_done + 30 * 8, par);
          if (NLAYERS > 1 && l + h == 0) mbar_wait(bar_phi + 8, 0);
          if (h) PROF(22);
          {
            const uint32_t pm0 = msk[1], pbit = O_BIT(l) * 0x10001u;
#pragma unroll
            for (int i = 0; i < 4; i++)
              stsm_x4_t(ta[i] + (h ? 3 : 12) * SLOT, PBIT(pack_bf16(o[i][0], o[i][1])), PBIT(pack_bf16(o[i + 4][0], o[i + 4][1])),
                        pack_bf16(o[i][2], o[i][3]), pack_bf16(o[i + 4][2], o[i + 4][3]));
          }
          WARP_STORE(&tm_os, sbase + (h ? 3 : 12) * SLOT, jj * 128 + h * 64, mm * 128);
          PROFH(11, 23);
          if (h) break;
          REST_P1(ASKEW);
          asm volatile("cp.async.bulk.wait_group.read 0;" ::: "memory");
          DRAIN_A(S1, 1, {});
        }
      } else {
        constexpr uint32_t par = 1;
        float st[32];
        const float c0 = rs0 * LOG2E, c1 = rs1 * LOG2E;
        { V_ADDR(pV, 0); STAGE_V(S0 + 64); }
        if (warp < 2) sts128(sbase + OFF_ONES + warp * 512 + lane * 16, 0x3F803F80u, 0x3F803F80u, 0x3F803F80u, 0x3F803F80u);
        scale32(st, S0, c0, c1);
        PIN(st, 32);
#define PHI_PIECE(c) { \
          e_[2 * (c)] = ex2(st[2 * (c)]); e_[2 * (c) + 1] = ex2(st[2 * (c) + 1]); \
          _Pragma("unroll") for (int k_ = 4 * (c); k_ < 4 * (c) + 4; k_++) m_[(c) >> 1] = (k_ & 7) ? fmaf(st[k_], st[k_], m_[(c) >> 1]) : st[k_] * st[k_]; \
          asm volatile("" : "+f"(e_[2 * (c)]), "+f"(e_[2 * (c) + 1]), "+f"(m_[(c) >> 1])); SCHED_FENCE(); }
#define PHI_FIN() { \
          big = __any_sync(0xffffffffu, !(fmaxf(fmaxf(m_[0], m_[1]), fmaxf(m_[2], m_[3])) < BIGLIM)); \
          if (__builtin_expect(big, 0)) { COPYN(e_, st, 16); } \
          _Pragma("unroll") for (int k_ = 0; k_ < 16; k_++) st[k_] = e_[k_]; \
          PIN(st, 16); }
#define KV_MMA(vs, IL) { \
          const uint32_t dp = dA0 + 12 * 1024 - wg * 2560, dv = dA0 + (vs) * 1024 + ((OFF_ONES - (vs) * SLOT - 16) << 12) - wg * (512 << 16); \
          STG_WAIT(); \
          fence_proxy_async_smem(); \
          wgmma_fence(); \
          _Pragma("unroll") for (int ks = 0; ks < 8; ks++) { \
            const uint64_t a = DESC(dp + ks * 128, 0x40000040), b = DESC(dv + ks * (64 - (64 << 16)), 0x80000020); \
            if ((IL) && ks) wgmma_fence(); \
            if (ks == 0) wgmma_n40<0, 1>(kv, a, b); else wgmma_n40<1, 1>(kv, a, b); \
            if (ks == 7) wgmma_commit(); \
            if (IL) PHI_PIECE(ks); } }
#define KV_RED1(i) if (h) red_v4(g_kv[l >> 1] + (jj * 4) * KVH + warp * 768 + lane * 4 + (i) * 128, S0[32 + (i) * 3], S0[33 + (i) * 3], S0[34 + (i) * 3], 1.f)
#define KV_REDS(n) { _Pragma("unroll") for (int i_ = 0; i_ < 6; i_++) if (((RPACE >> (4 * i_)) & 15) == (n)) KV_RED1(i_); }
#define KV_SEND(kp) { \
          float sd[9]; \
          _Pragma("unroll") for (int i = 0; i < 8; i++) { (kp)[i] = kv[i]; sd[i] = kv[8 + i]; } \
          (kp)[8] = rank ? kv[18] : kv[16]; sd[8] = rank ? kv[16] : kv[18]; \
          const uint32_t ra = sbase + peer + (warp * 32 + lane) * 4, rb = bar_kx + peer; \
          if (elect_one()) mbar_expect_tx(bar_kx, 1152); \
          _Pragma("unroll") for (int i = 0; i < 2; i++) \
            asm volatile("st.async.weak.shared::cluster.mbarrier::complete_tx::bytes.v4.f32 [%0], {%1, %2, %3, %4}, [%5];" \
                         :: "r"(ra + (warp * 32 + lane) * 12 + OFF_PHI + i * 4096), "f"(sd[4 * i]), "f"(sd[4 * i + 1]), "f"(sd[4 * i + 2]), "f"(sd[4 * i + 3]), "r"(rb) : "memory"); \
          asm volatile("st.async.weak.shared::cluster.mbarrier::complete_tx::bytes.f32 [%0], %1, [%2];" :: "r"(ra + OFF_LNB), "f"(sd[8]), "r"(rb) : "memory"); }
#define KV_RECV(kp, hp) { \
          float r_[9]; \
          float* kvg = g_kv[l >> 1] + (jj * 4 + (hp) * 2) * KVH + warp * 768 + rank * 384 + lane * 4; \
          mbar_wait(bar_kx, l >> 1); \
          _Pragma("unroll") for (int i = 0; i < 2; i++) \
            asm volatile("ld.shared.v4.f32 {%0, %1, %2, %3}, [%4];" : "=f"(r_[4 * i]), "=f"(r_[4 * i + 1]), "=f"(r_[4 * i + 2]), "=f"(r_[4 * i + 3]) \
                         : "r"(sbase + OFF_PHI + i * 4096 + (warp * 32 + lane) * 16) : "memory"); \
          r_[8] = lds32f(sbase + OFF_LNB + (warp * 32 + lane) * 4); \
          _Pragma("unroll") for (int i = 0; i < 3; i++) red_v4(kvg + i * 128, (kp)[3 * i] + r_[3 * i], (kp)[3 * i + 1] + r_[3 * i + 1], (kp)[3 * i + 2] + r_[3 * i + 2], 2.f); }
#define KV_LOAD(hp) { \
          const uint4* kvg = reinterpret_cast<const uint4*>(g_kv[l >> 1] + (jj * 4 + (hp) * 2) * KVH) + warp * 192 + lane; \
          _Pragma("unroll") for (int i = 0; i < 6; i++) v[i] = ld_b128(kvg + i * 32); }
#define KVV(i) __uint_as_float((i) % 3 == 0 ? v[(i) / 3].x : ((i) % 3 == 1 ? v[(i) / 3].y : v[(i) / 3].z))
#define KV_TILE(hp) { \
          _Pragma("unroll 1") for (int it = 0; it < (1 << 16); it++) { \
            if (__all_sync(0xffffffffu, (v[0].w & v[1].w & v[2].w & v[3].w & v[4].w & v[5].w) == 0x41800000u)) break; \
            RETRY_COUNT(); \
            KV_LOAD(hp); \
          } \
          if (hp) PROF(26); else PROF(25); \
          const uint32_t e = lane & 7, jt = ((lane >> 1) & 4) + (e >> 1); \
          const uint32_t row = ((((warp >> 1) ^ wg) & 1) << 5) + ((jt & 1) << 4) + ((warp & 1) << 3) + (jt & 6) + (e & 1); \
          const uint32_t kd = pV + wg * 8192 + row * 128, ksw = (row & 7) << 4; \
          _Pragma("unroll") for (int i = 0; i < 2; i++) \
            stsm_x4(kd + ((i * 32 + lhi) ^ ksw), pack_bf16(KVV(i * 9), KVV(i * 9 + 1)), pack_bf16(KVV(i * 9 + 2), KVV(i * 9 + 3)), \
                    pack_bf16(KVV(i * 9 + 4), KVV(i * 9 + 5)), pack_bf16(KVV(i * 9 + 6), KVV(i * 9 + 7))); \
          stsm_x4(kd + ((64u + lhi) ^ ksw), pack_bf16(KVV(8), 1.f), pack_bf16(KVV(17), 1.f), 0u, 0u); }
#pragma unroll 1
        for (int h = 0; h < 2; h++) {
          PROFH(4, 6);
          PUMP0();
          LANE_CONSTS();
          const uint32_t dsw = (uint32_t)(g ^ (2 * t)) << 4, dst = ((t & 2) ? pK : sbase + 12 * SLOT) + (r0 + g) * 128;
          float e[16], f[16];
          KV_REDS(1);
          float sa = exps16_<0>(e, st);
          exps16_fix<0>(e, st, sa);
          asm volatile("" : "+f"(sa)); PIN(e, 16); PUMP0();
          if (h) STG_WAIT();
          KV_REDS(2);
          store16(e, sa, dst, dsw, 4);
          float sb = exps16_<1>(f, st);
          exps16_fix<1>(f, st, sb);
          asm volatile("" : "+f"(sb)); PIN(f, 16); PUMP0();
          KV_REDS(3);
          store16(f, sb, dst, dsw, 0);
          float sc = exps16_<0>(e, st + 2);
          exps16_fix<0>(e, st + 2, sc);
          asm volatile("" : "+f"(sc)); PIN(e, 16); PUMP0();
          KV_REDS(4);
          store16(e, sc, dst + 1024, dsw, 4);
          float sd = exps16_<1>(f, st + 2);
          exps16_fix<1>(f, st + 2, sd);
          asm volatile("" : "+f"(sd)); PIN(f, 16); PUMP0();
          store16(f, sd, dst + 1024, dsw, 0);
          PROFH(5, 7);
          if (h) break;
          {
            float kv[20];
            ACC_DEF(kv, 20);
            STG_ARRIVE();
            float e_[16], m_[4];
            KV_MMA(11, 0);
            PUMP0();
            ACC_FENCE(kv, 20);
            STG_ARRIVE();
            scale32(st, S0 + 32, c0, c1);
            PIN(st, 32);
            {
              COPYN(S0 + 32, kv, 8); COPYN(S0 + 40, kv + 16, 1); COPYN(S0 + 41, kv + 8, 8); COPYN(S0 + 49, kv + 18, 1);
              const int h = 1;
              KV_REDS(0);
            }
          }
        }
        bool big;
        uint4 v[6];
        {
          float kv[20];
          { LANE_CONSTS(); KV_LOAD(0); }
          mbar_wait(bar_stat2, par);
          ub = bar_full + 240;
          LNSTEP(S1, 1);
          PUMP1();
          if (wg == 0) bar_sync<BAR_SKEW, 256>();
          QSTEP(S1, RA_CUR, 1);
          if (wg == 1) bar_arrive<BAR_SKEW, 256>();
          QREL();
          { LANE_CONSTS(); KV_TILE(0); }
          LANE_CONSTS();
          V_ADDR(sbase + 3 * SLOT, rank * 32);
          PINU(va_, 2);
          mbar_wait(bar_done + 30 * 8, par);
          wgmma_wait<0>();
          ACC_FENCE(S1, 96);
          PROF(13);
          STAGE_V(S1 + 64);
          STG_ARRIVE();
          REL(bar_done + 31 * 8);
          scale32(st, S1, c0, c1);
          PIN(st, 32);
          PROF(16);
          ACC_DEF(kv, 20);
          float e_[16], m_[4];
          KV_MMA(3, 1);
          SCHED_FENCE();
          PROF(14);
          PHI_FIN();
          SCHED_FENCE();
          PROF(15);
          wgmma_wait<0>();
          ACC_FENCE(kv, 20);
          PROF(12);
          { float kp[9]; KV_SEND(kp); _Pragma("unroll") for (int i = 0; i < 3; i++) v[i] = make_uint4(__float_as_uint(kp[3 * i]), __float_as_uint(kp[3 * i + 1]), __float_as_uint(kp[3 * i + 2]), 0u); }
#define VDEF(i0) _Pragma("unroll") for (int i = (i0); i < 6; i++) asm volatile("" : "=r"(v[i].x), "=r"(v[i].y), "=r"(v[i].z), "=r"(v[i].w))
          VDEF(3);
          PROF(17);
        }
#pragma unroll 1
        for (int h = 0; h < 2; h++) {
          const uint32_t pO = sbase + (h ? 3 : 8) * SLOT;
          LANE_CONSTS();
          uint32_t fq[32];
          if (h) { KV_LOAD(1); phiq_a(st, big); PIN(st, 16); PROF(31); }
          PROFH(18, 32);
          SCHED_FENCE();
          phiq_b<1>(fq, st, big); PINU(fq, 16); PIN(st + 16, 16);
          SCHED_FENCE();
          PROFH(8, 9);
          if (h) {
            asm volatile("cp.async.bulk.wait_group.read 0;" ::: "memory");
            mbar_wait(bar_lx, par);
            PROF(30);
            KV_TILE(1);
            STG_ARRIVE();
          }
          SCHED_FENCE();
          if (h == 0) {
            float kp[9];
#pragma unroll
            for (int i = 0; i < 9; i++) kp[i] = KVV(i);
            KV_RECV(kp, 1);
            SCHED_FENCE();
          }
          phiq_b<0>(fq + 16, st + 16, big); PINU(fq + 16, 16);
          PROFH(10, 21);
          if (h) { STG_WAIT(); fence_proxy_async_smem(); }
          wgmma_wait<0>();
          ACC_FENCE(S1, 64);
          PROFH(19, 33);
          float o[4][20];
#define O_MMA(hh) { \
            const uint64_t db = make_desc(pV + (hh) * 8192, 16, 1024); \
            ACC_DEF(o[(hh) * 2], 20); ACC_DEF(o[(hh) * 2 + 1], 20); \
            wgmma_fence(); \
            wgmma_n40_rs<0>(o[(hh) * 2], fq + (hh) * 16, db + 256); wgmma_n40_rs<0>(o[(hh) * 2 + 1], fq + (hh) * 16 + 8, db); \
            wgmma_n40_rs<1>(o[(hh) * 2], fq + (hh) * 16 + 4, db + 384); wgmma_n40_rs<1>(o[(hh) * 2 + 1], fq + (hh) * 16 + 12, db + 128); \
            wgmma_commit(); }
          O_MMA(0);
          SCHED_FENCE();
          PMASKS(true, O_BIT(l));
#pragma unroll
          for (int hh = 0; hh < 2; hh++) {
            wgmma_wait<0>();
            ACC_FENCE(o[hh * 2], 20); ACC_FENCE(o[hh * 2 + 1], 20);
            if (!hh) { O_MMA(1); SCHED_FENCE(); }
            if (hh) PROFH(22, 24);
            const float* x = o[hh * 2];
            const float* y = o[hh * 2 + 1];
            const float sx0 = x[17] * 0x1p-40f, sy0 = y[17] * 0x1p-40f, sx1 = x[19] * 0x1p-40f, sy1 = y[19] * 0x1p-40f;
            const float i0 = rcp_fast(fmaf(fmaf(x[17], 1e-6f, x[16]), sy0, y[16] * sx0)), i1 = rcp_fast(fmaf(fmaf(x[19], 1e-6f, x[18]), sy1, y[18] * sx1));
            const float ax0 = sy0 * i0, ay0 = sx0 * i0, ax1 = sy1 * i1, ay1 = sx1 * i1;
#pragma unroll
            for (int dp = 0; dp < 2; dp++)
              stsm_x4(pO + srowoff + ((hh * 64 + dp * 32 + lhi) ^ lsw),
                      PBIT(pack_bf16(fmaf(x[dp * 8], ax0, y[dp * 8] * ay0), fmaf(x[dp * 8 + 1], ax0, y[dp * 8 + 1] * ay0))),
                      PBIT(pack_bf16(fmaf(x[dp * 8 + 2], ax1, y[dp * 8 + 2] * ay1), fmaf(x[dp * 8 + 3], ax1, y[dp * 8 + 3] * ay1))),
                      (pack_bf16(fmaf(x[dp * 8 + 4], ax0, y[dp * 8 + 4] * ay0), fmaf(x[dp * 8 + 5], ax0, y[dp * 8 + 5] * ay0))),
                      (pack_bf16(fmaf(x[dp * 8 + 6], ax1, y[dp * 8 + 6] * ay1), fmaf(x[dp * 8 + 7], ax1, y[dp * 8 + 7] * ay1))));
          }
          WARP_STORE(&tm_os, pO, jj * 128 + h * 64, mm * 128);
          PROFH(20, 34);
          if (h) break;
          float T_[64];
          scale32(st, S1 + 32, c0, c1);
          PIN(st, 32);
          ACC_DEF(T_, 64);
          XM_ISSUE(); wgmma_commit();
          SCHED_FENCE();
          big = any_big(st);
          SCHED_FENCE();
          PROF(27);
          wgmma_wait<0>(); XM_DONE();
          PROF(28);
          bar_wg(wg);
          WSTEP();
          SCHED_FENCE();
          VDEF(0);
          PROF(29);
        }
      }
      __syncwarp();
      if (elect_one()) mbar_arrive_local(bar_epi);
      bar_wg(wg);
#pragma unroll 1
      while (ub < bar_full + 384) {
        if (FSK && l == NLAYERS - 1 && wg == 0 && ub == bar_full + 384 - 8 * FSK) bar_sync<BAR_SKEW, 256>();
        if (FSK && l == NLAYERS - 1 && wg == 1 && ub == bar_full + 376) { mbar_wait(ub, par); bar_arrive<BAR_SKEW, 256>(); }
        WSTEP();
        if (ub == bar_full + 8 * 41) { asm volatile("cp.async.bulk.wait_group.read 0;" ::: "memory"); PROF(35); }
        if (ub == bar_full + 8 * 42) PROF(36);
      }
      {
        float Wb[32];
        LANE_CONSTS();
        TILE_CONSTS(pK, l < NLAYERS - 1, X_BIT(l));
        if (l < NLAYERS - 1) mbar_wait(bar_full, par ^ 1);
        wgmma_wait<0>();
        ACC_FENCE(S1, 64);
        COPYN(Wb, S1 + 32, 32);
        PROF(37);
        uint32_t xa[16];
#pragma unroll
        for (int i = 0; i < 16; i++) { const uint32_t w = pack_bf16(S1[2 * i], S1[2 * i + 1]); xa[i] = (i & 2) ? w : PBIT(w); }
        PINU(xa, 16);
#define XA_OUT() _Pragma("unroll") for (int j = 0; j < 4; j++) stsm_x4(ta[j], xa[4 * j], xa[4 * j + 1], xa[4 * j + 2], xa[4 * j + 3])
        if (l == NLAYERS - 1) {
          XA_OUT();
          const uint32_t src = pK + (r0 + (lane >> 3)) * 128 + (((lane ^ (lane >> 3)) & 7) << 4);
          uint4* dst = reinterpret_cast<uint4*>(prm.out + (size_t)(mm * 128 + (warp >> 1) * 32 + (warp & 1) + (lane >> 3) * 2) * D_MODEL + jj * 128) + (lane & 7);
#pragma unroll
          for (int pc = 0; pc < 2; pc++) {
            if (pc) { PMASKS(false, 0); X_OUT(1, Wb); }
            __syncwarp();
            uint4 y[4];
#pragma unroll
            for (int i = 0; i < 4; i++)
              asm volatile("ld.shared.v4.u32 {%0, %1, %2, %3}, [%4];" : "=r"(y[i].x), "=r"(y[i].y), "=r"(y[i].z), "=r"(y[i].w) : "r"((src + pc * SLOT + i * 512) ^ ((i & 1) << 6)) : "memory");
#pragma unroll
            for (int i = 0; i < 4; i++) dst[pc * 8 + i * 1024] = y[i];
            if (pc) PROF(39); else PROF(38);
          }
          break;
        }
        PROF(38);
        XA_OUT();
        ACC_DEF(S0, 96);
        wgmma_fence();
        wgmma_n192_rs<0>(S0, xa, dB0);
#pragma unroll
        for (int k = 1; k < RSK; k++) wgmma_n192_rs<1>(S0, xa + 4 * k, dB0 + 128 * k);
        wgmma_commit();
        WARP_STORE(&tm_os, pK, jj * 128, mm * 128 + S_LEN);
        if (RSK < 4) {
          wgmma_fence();
#pragma unroll
          for (int k = RSK; k < 4; k++) wgmma_n192_rs<1>(S0, xa + 4 * k, dB0 + 128 * k);
          wgmma_commit();
        }
        { const int ln_ = l + 1, l = ln_; const uint32_t ub = bar_full; (void)l; (void)ub; PROFS(); }
        REL(bar_done + 47 * 8);
        ub = bar_full + 8;
        PROF(39);
        { PMASKS(false, 0); X_OUT(1, Wb); }
        fence_proxy_async_smem();
      }
    }
    cluster_sync();
    if (threadIdx.x == 0) PROFT(487);
  }
}

typedef CUresult (*PFN_encode)(CUtensorMap*, CUtensorMapDataType, cuuint32_t, void*, const cuuint64_t*, const cuuint64_t*,
                               const cuuint32_t*, const cuuint32_t*, CUtensorMapInterleave, CUtensorMapSwizzle,
                               CUtensorMapL2promotion, CUtensorMapFloatOOBfill);

CUtensorMap make_map(PFN_encode enc, const void* ptr, uint64_t inner, uint64_t outer, uint32_t box_inner, uint32_t box_outer,
                     CUtensorMapSwizzle swz = CU_TENSOR_MAP_SWIZZLE_128B, int promo = CU_TENSOR_MAP_L2_PROMOTION_L2_256B) {
  CUtensorMap m;
  cuuint64_t dims[2] = {inner, outer};
  cuuint64_t strides[1] = {inner * 2};
  cuuint32_t box[2] = {box_inner, box_outer};
  cuuint32_t es[2] = {1, 1};
  enc(&m, CU_TENSOR_MAP_DATA_TYPE_BFLOAT16, 2, const_cast<void*>(ptr), dims, strides, box, es, CU_TENSOR_MAP_INTERLEAVE_NONE,
      swz, (CUtensorMapL2promotion)promo, CU_TENSOR_MAP_FLOAT_OOB_FILL_NONE);
  return m;
}

CUtensorMap make_tile_map(PFN_encode enc, const void* ptr, uint64_t rows, bool by_parity, int promo) {
  CUtensorMap m;
  cuuint64_t dims[4] = {D_MODEL, 16, 2, rows / 32};
  cuuint64_t strides[3] = {by_parity ? 4096u : 2048u, by_parity ? 2048u : 32768u, 65536};
  cuuint32_t box[4] = {64, 16, 2, 4};
  cuuint32_t es[4] = {1, 1, 1, 1};
  enc(&m, CU_TENSOR_MAP_DATA_TYPE_BFLOAT16, 4, const_cast<void*>(ptr), dims, strides, box, es, CU_TENSOR_MAP_INTERLEAVE_NONE,
      CU_TENSOR_MAP_SWIZZLE_128B, (CUtensorMapL2promotion)promo, CU_TENSOR_MAP_FLOAT_OOB_FILL_NONE);
  return m;
}

}

extern "C" void kernel_launch(void* const* d_in, const int* in_sizes, int n_in, void* d_out, int out_size) {
  (void)in_sizes; (void)n_in; (void)out_size;
  static PFN_encode enc = nullptr;
  if (!enc) {
    void* fn = nullptr;
    cudaDriverEntryPointQueryResult qr;
    cudaGetDriverEntryPoint("cuTensorMapEncodeTiled", &fn, cudaEnableDefault, &qr);
    enc = (PFN_encode)fn;
    cudaFuncSetAttribute(mega_kernel, cudaFuncAttributeMaxDynamicSharedMemorySize, SMEM_BYTES);
  }
  Params prm;
  prm.wA_o = (const __nv_bfloat16*)d_in[2];
  prm.wB_qkv = (const __nv_bfloat16*)d_in[4];
  prm.wB_o = (const __nv_bfloat16*)d_in[6];
  prm.out = (__nv_bfloat16*)d_out;
  void *obuf = nullptr, *wf = nullptr, *fl = nullptr;
  cudaGetSymbolAddress(&fl, g_flags);
  prm.epoch = &static_cast<Flags*>(fl)->epoch.v;
  cudaGetSymbolAddress(&obuf, g_obuf);
  cudaGetSymbolAddress(&wf, g_wfold);
  CUtensorMap tm_x0 = make_tile_map(enc, d_in[0], S_LEN, true, XPROMO);
  CUtensorMap tm_os = make_map(enc, obuf, D_MODEL, 2 * S_LEN, 64, 16);
  CUtensorMap tm_o = make_tile_map(enc, obuf, 2 * S_LEN, false, OPROMO);
  CUtensorMap tm_wf = make_map(enc, wf, 2048, D_MODEL, 64, 32);
  CUtensorMap tm_wqA = make_map(enc, d_in[1], 3 * D_MODEL, D_MODEL, 64, 32, CU_TENSOR_MAP_SWIZZLE_128B, WPROMO);
  CUtensorMap tm_wqB = make_map(enc, prm.wB_qkv, 3 * D_MODEL, D_MODEL, 64, 32);
  CUtensorMap tm_woA = make_map(enc, prm.wA_o, D_MODEL, D_MODEL, 64, 64);
  CUtensorMap tm_woB = make_map(enc, prm.wB_o, D_MODEL, D_MODEL, 64, 64);
  CUtensorMap tm_phi = make_map(enc, d_in[5], 32, 1024, 32, 128, CU_TENSOR_MAP_SWIZZLE_64B);
  mega_kernel<<<NMAIN + NAUX, 384, SMEM_BYTES>>>(prm, tm_x0, tm_os, tm_o, tm_wf, tm_wqA, tm_wqB, tm_woA, tm_woB, tm_phi);
}
```

```cpp
#include <cuda_runtime.h>
#include <cuda.h>
#include <cuda_bf16.h>
#include <stdint.h>

#define NLAYERS 4

#define HPUMP2 1
#define ASKEW 2
#define FPUMP 3
#define PFGAP 100
#define POLLGAP 120
#define HW1 30
#define XPACE 0x06050401000000ull
#define HW0 18
#define XD 4
#define WFGAP 10
#define EARLY 4
#define BIGLIM 3600.f
#define SUMLO 0x1p-100f
#define SUMHI 0x1p100f
#define XPROMO 2
#define OPROMO 3
#define STAG2 0
#define WPROMO 3
#define SB0 2
#define SB1 4
#define SB2 6
#define PROWS 7
#define SPD0 0
#define SPD1 0
#define SPD2 300
#define FRB 0x3535353535ull
#define NOB 0xFFFFFF00u
#define NO1 ~0u
#define NOX ~0u
#define FD0 3
#define CSGAP 300
#define AUXORD 0x76543210
#define FSK 3
#define OWNW0 1
#define OWNW1 2
#define RPACE 0x221100
#define RSK 2
namespace {

constexpr int S_LEN = 2048, D_MODEL = 1024;
constexpr int NAUX = 4, NMAIN = 128;
constexpr int SLOT = 16384;
constexpr int QST = 24576;
constexpr int OFF_RA = 6 * SLOT, OFF_S = 10 * SLOT;
constexpr int OFF_HALO = 13 * SLOT, OFF_LNB = OFF_HALO  , OFF_ONES = OFF_HALO + 3072;
constexpr int OFF_ST = OFF_HALO + 7168  , OFF_ID = OFF_HALO + 7680, OFF_PHI = OFF_HALO + 8192;
constexpr int OFF_BAR = 14 * SLOT;
constexpr int OFF_LNA = OFF_BAR + 1024;
constexpr int SMEM_BYTES = OFF_LNA + 2048;
#define WO_ASLOT(par) ((par) ? 0x9876CAB39876CA98ull : 0xBC7698A3BC7698BCull)
constexpr unsigned long long WO_BSLOT = 0x5432105421054210ull;
__device__ __forceinline__ int srcb(int j, int i) { return (i + (i >= j)) & 7; }
__device__ __forceinline__ int kslice(int j, int i) { return i < 2 ? 2 * j + i : (i < 9 ? 2 * srcb(j, i - 2) : 2 * srcb(j, i - 9) + 1); }
__device__ __forceinline__ int wslice(int j, int s) { return 2 * ((s & 7) ? srcb(j, (s & 7) - 1) : j) + (s >> 3); }
constexpr int KVH = 6 * 128 * 4;

struct __align__(128) Flag { unsigned v; unsigned pad[31]; };
struct Flags {
  Flag xready[4][16];
  Flag wfready[8];
  Flag done;
  Flag epoch;
};

__device__ Flags g_flags;
__device__ __nv_bfloat16 g_obuf[2 * S_LEN * D_MODEL];
#define O_BIT(l) ((epoch * NLAYERS + (l) + 1) & 1u)
#define X_BIT(l) ((epoch * (NLAYERS - 1) + (l) + 1) & 1u)
__device__ __nv_bfloat16 g_wfold[D_MODEL * 2048];
__device__ uint4 g_halo[16 * 8 * 512];
__device__ __align__(128) float g_kv[2][32 * KVH];
__device__ __align__(128) uint2 g_colsum[2][1536][2];
__device__ __align__(128) uint2 g_stats[S_LEN * 8];
#define H_BIT(l) (NLAYERS > 2 ? (uint32_t)((l) == 0) : (ep1 & 1))
#define STAT_TAG(l) ((ep1 * NLAYERS + (l) + 1) & 3u)

#define RETRY_COUNT()
#define PRL 3
#define PROFL 1
#define PROFW 0
#define PROF2V() do {} while (0)
#define PROFT(i) do {} while (0)
#define PROF(i) do {} while (0)
#define PROFH(i, j) do {} while (0)
#define PROFL3(i) do {} while (0)

__device__ __forceinline__ uint32_t smem_u32(const void* p) { return (uint32_t)__cvta_generic_to_shared(p); }
__device__ __forceinline__ bool elect_one() {
  uint32_t p;
  asm volatile("{\n.reg .pred p;\nelect.sync _|p, 0xffffffff;\nselp.u32 %0, 1, 0, p;\n}\n" : "=r"(p));
  return p != 0;
}
__device__ __forceinline__ void mbar_init(uint32_t bar, uint32_t cnt) {
  asm volatile("mbarrier.init.shared::cta.b64 [%0], %1;" :: "r"(bar), "r"(cnt));
}
__device__ __forceinline__ void mbar_expect_tx(uint32_t bar, uint32_t bytes) {
  asm volatile("mbarrier.arrive.expect_tx.shared::cta.b64 _, [%0], %1;" :: "r"(bar), "r"(bytes) : "memory");
}
#define mbar_wait(bar, parity) \
  asm volatile("{\n.reg .pred p, q;\nW_%=:\nmbarrier.try_wait.parity.shared::cta.b64 p, [%1], %2;\nadd.s32 %0, %0, -1;\n" \
               "setp.gt.and.s32 q, %0, 0, !p;\n@q bra.uni W_%=;\n}\n" : "+r"(budget) : "r"((uint32_t)(bar)), "r"((uint32_t)(parity)) : "memory")
#define mbar_wait_sl(bar, parity) \
  asm volatile("{\n.reg .pred p, q;\nW_%=:\nmbarrier.try_wait.parity.shared::cta.b64 p, [%1], %2, 20000;\nadd.s32 %0, %0, -64;\n" \
               "setp.gt.and.s32 q, %0, 0, !p;\n@q bra.uni W_%=;\n}\n" : "+r"(budget) : "r"((uint32_t)(bar)), "r"((uint32_t)(parity)) : "memory")
__device__ __forceinline__ void mbar_arrive_local(uint32_t bar) {
  asm volatile("mbarrier.arrive.shared::cta.b64 _, [%0];" :: "r"(bar) : "memory");
}
__device__ __forceinline__ void tma_load_2d(uint32_t dst, const CUtensorMap* tm, uint32_t bar, int c0, int c1) {
  asm volatile("cp.async.bulk.tensor.2d.shared::cluster.global.mbarrier::complete_tx::bytes [%0], [%1, {%3, %4}], [%2];"
               :: "r"(dst), "l"(tm), "r"(bar), "r"(c0), "r"(c1) : "memory");
}
__device__ __forceinline__ void tma_load_2d_mc(uint32_t dst, const CUtensorMap* tm, uint32_t bar, int c0, int c1) {
  asm volatile("cp.async.bulk.tensor.2d.shared::cluster.global.mbarrier::complete_tx::bytes.multicast::cluster [%0], [%1, {%3, %4}], [%2], %5;"
               :: "r"(dst), "l"(tm), "r"(bar), "r"(c0), "r"(c1), "h"((uint16_t)3) : "memory");
}
__device__ __forceinline__ void tma_store_2d(const CUtensorMap* tm, uint32_t src, int c0, int c1) {
  asm volatile("cp.async.bulk.tensor.2d.global.shared::cta.bulk_group [%0, {%2, %3}], [%1];"
               :: "l"(tm), "r"(src), "r"(c0), "r"(c1) : "memory");
}
__device__ __forceinline__ void tma_load_t(uint32_t dst, const CUtensorMap* tm, uint32_t bar, int c0, int row) {
  asm volatile("cp.async.bulk.tensor.4d.shared::cluster.global.mbarrier::complete_tx::bytes [%0], [%1, {%3, %5, %5, %4}], [%2];"
               :: "r"(dst), "l"(tm), "r"(bar), "r"(c0), "r"(row >> 5), "r"(0) : "memory");
}
__device__ __forceinline__ void tma_store_t(const CUtensorMap* tm, uint32_t src, int c0, int row) {
  asm volatile("cp.async.bulk.tensor.4d.global.shared::cta.bulk_group [%0, {%2, %4, %4, %3}], [%1];"
               :: "l"(tm), "r"(src), "r"(c0), "r"(row >> 5), "r"(0) : "memory");
}
__device__ __forceinline__ void bulk_commit_wait() {
  asm volatile("cp.async.bulk.commit_group;\ncp.async.bulk.wait_group 0;" ::: "memory");
}
__device__ __forceinline__ void prefetch_tmap(const CUtensorMap* tm) {
  asm volatile("prefetch.tensormap [%0];" :: "l"(tm) : "memory");
}
__device__ __forceinline__ void fence_proxy_async_global() { asm volatile("fence.proxy.async.global;" ::: "memory"); }
__device__ __forceinline__ void fence_proxy_async_smem() { asm volatile("fence.proxy.async.shared::cta;" ::: "memory"); }
__device__ __forceinline__ unsigned ld_relaxed(const unsigned* p) {
  unsigned v;
  asm volatile("ld.relaxed.gpu.global.u32 %0, [%1];" : "=r"(v) : "l"(p) : "memory");
  return v;
}
__device__ __forceinline__ void fence_acquire() { asm volatile("fence.acquire.gpu;" ::: "memory"); }
__device__ __forceinline__ void wait_flag(const unsigned* p, unsigned target) {
  int it = 0;
  while ((int)(ld_relaxed(p) - target) < 0 && ++it < (1 << 20)) {}
  fence_acquire();
}
__device__ __forceinline__ void signal_release(unsigned* p) {
  asm volatile("red.release.gpu.global.add.u32 [%0], 1;" :: "l"(p) : "memory");
}
template <int ID, int N> __device__ __forceinline__ void bar_arrive() { asm volatile("bar.arrive %0, %1;" :: "n"(ID), "n"(N) : "memory"); }
template <int ID, int N> __device__ __forceinline__ void bar_sync() { asm volatile("bar.sync %0, %1;" :: "n"(ID), "n"(N) : "memory"); }
__device__ __forceinline__ void bar_wg(int wg) { asm volatile("bar.sync %0, 128;" :: "r"(2 + wg) : "memory"); }
__device__ __forceinline__ void cluster_sync() {
  asm volatile("barrier.cluster.arrive.relaxed.aligned;\nbarrier.cluster.wait.aligned;" ::: "memory");
}
__device__ __forceinline__ void cluster_wait() { asm volatile("barrier.cluster.wait.acquire.aligned;" ::: "memory"); }
enum { BAR_X1 = 7, BAR_WF = 8  , BAR_SKEW = 10 };

__device__ __forceinline__ void wgmma_fence() { asm volatile("wgmma.fence.sync.aligned;" ::: "memory"); }
__device__ __forceinline__ void wgmma_commit() { asm volatile("wgmma.commit_group.sync.aligned;" ::: "memory"); }
template <int N> __device__ __forceinline__ void wgmma_wait() { asm volatile("wgmma.wait_group.sync.aligned %0;" :: "n"(N) : "memory"); }

template <int scale_d, int tnsp_b = 1> __device__ __forceinline__ void wgmma_n192(float* d, uint64_t descA, uint64_t descB) {
  asm volatile("{\n.reg .pred p;\nsetp.ne.b32 p, %98, 0;\n"
               "wgmma.mma_async.sync.aligned.m64n192k16.f32.bf16.bf16 {%0,%1,%2,%3,%4,%5,%6,%7,%8,%9,%10,%11,%12,%13,%14,%15,%16,%17,%18,%19,%20,%21,%22,%23,%24,%25,%26,%27,%28,%29,%30,%31,%32,%33,%34,%35,%36,%37,%38,%39,%40,%41,%42,%43,%44,%45,%46,%47,%48,%49,%50,%51,%52,%53,%54,%55,%56,%57,%58,%59,%60,%61,%62,%63,%64,%65,%66,%67,%68,%69,%70,%71,%72,%73,%74,%75,%76,%77,%78,%79,%80,%81,%82,%83,%84,%85,%86,%87,%88,%89,%90,%91,%92,%93,%94,%95}, %96, %97, p, 1, 1, 0, %99;\n}\n"
               : "+f"(d[0]), "+f"(d[1]), "+f"(d[2]), "+f"(d[3]), "+f"(d[4]), "+f"(d[5]), "+f"(d[6]), "+f"(d[7]), "+f"(d[8]), "+f"(d[9]), "+f"(d[10]), "+f"(d[11]), "+f"(d[12]), "+f"(d[13]), "+f"(d[14]), "+f"(d[15]), "+f"(d[16]), "+f"(d[17]), "+f"(d[18]), "+f"(d[19]), "+f"(d[20]), "+f"(d[21]), "+f"(d[22]), "+f"(d[23]), "+f"(d[24]), "+f"(d[25]), "+f"(d[26]), "+f"(d[27]), "+f"(d[28]), "+f"(d[29]), "+f"(d[30]), "+f"(d[31]), "+f"(d[32]), "+f"(d[33]), "+f"(d[34]), "+f"(d[35]), "+f"(d[36]), "+f"(d[37]), "+f"(d[38]), "+f"(d[39]), "+f"(d[40]), "+f"(d[41]), "+f"(d[42]), "+f"(d[43]), "+f"(d[44]), "+f"(d[45]), "+f"(d[46]), "+f"(d[47]), "+f"(d[48]), "+f"(d[49]), "+f"(d[50]), "+f"(d[51]), "+f"(d[52]), "+f"(d[53]), "+f"(d[54]), "+f"(d[55]), "+f"(d[56]), "+f"(d[57]), "+f"(d[58]), "+f"(d[59]), "+f"(d[60]), "+f"(d[61]), "+f"(d[62]), "+f"(d[63]), "+f"(d[64]), "+f"(d[65]), "+f"(d[66]), "+f"(d[67]), "+f"(d[68]), "+f"(d[69]), "+f"(d[70]), "+f"(d[71]), "+f"(d[72]), "+f"(d[73]), "+f"(d[74]), "+f"(d[75]), "+f"(d[76]), "+f"(d[77]), "+f"(d[78]), "+f"(d[79]), "+f"(d[80]), "+f"(d[81]), "+f"(d[82]), "+f"(d[83]), "+f"(d[84]), "+f"(d[85]), "+f"(d[86]), "+f"(d[87]), "+f"(d[88]), "+f"(d[89]), "+f"(d[90]), "+f"(d[91]), "+f"(d[92]), "+f"(d[93]), "+f"(d[94]), "+f"(d[95])
               : "l"(descA), "l"(descB), "n"(scale_d), "n"(tnsp_b));
}
template <int scale_d> __device__ __forceinline__ void wgmma4_n192(float* d, uint32_t da, uint32_t db) {
#define R_ "{%0,%1,%2,%3,%4,%5,%6,%7,%8,%9,%10,%11,%12,%13,%14,%15,%16,%17,%18,%19,%20,%21,%22,%23,%24,%25,%26,%27,%28,%29,%30,%31,%32,%33,%34,%35,%36,%37,%38,%39,%40,%41,%42,%43,%44,%45,%46,%47,%48,%49,%50,%51,%52,%53,%54,%55,%56,%57,%58,%59,%60,%61,%62,%63,%64,%65,%66,%67,%68,%69,%70,%71,%72,%73,%74,%75,%76,%77,%78,%79,%80,%81,%82,%83,%84,%85,%86,%87,%88,%89,%90,%91,%92,%93,%94,%95}"
  asm volatile("{\n.reg .pred p, q;\n.reg .b64 a, b;\nsetp.ne.b32 p, %98, 0;\nsetp.eq.b32 q, 0, 0;\nmov.b64 a, {%96, 0x40000040};\nmov.b64 b, {%97, 0x40000040};\n"
               "wgmma.mma_async.sync.aligned.m64n192k16.f32.bf16.bf16 " R_ ", a, b, p, 1, 1, 0, 1;\nadd.s64 a, a, 2;\nadd.s64 b, b, 128;\n"
               "wgmma.mma_async.sync.aligned.m64n192k16.f32.bf16.bf16 " R_ ", a, b, q, 1, 1, 0, 1;\nadd.s64 a, a, 2;\nadd.s64 b, b, 128;\n"
               "wgmma.mma_async.sync.aligned.m64n192k16.f32.bf16.bf16 " R_ ", a, b, q, 1, 1, 0, 1;\nadd.s64 a, a, 2;\nadd.s64 b, b, 128;\n"
               "wgmma.mma_async.sync.aligned.m64n192k16.f32.bf16.bf16 " R_ ", a, b, q, 1, 1, 0, 1;\n}\n"
               : "+f"(d[0]), "+f"(d[1]), "+f"(d[2]), "+f"(d[3]), "+f"(d[4]), "+f"(d[5]), "+f"(d[6]), "+f"(d[7]), "+f"(d[8]), "+f"(d[9]), "+f"(d[10]), "+f"(d[11]), "+f"(d[12]), "+f"(d[13]), "+f"(d[14]), "+f"(d[15]), "+f"(d[16]), "+f"(d[17]), "+f"(d[18]), "+f"(d[19]), "+f"(d[20]), "+f"(d[21]), "+f"(d[22]), "+f"(d[23]), "+f"(d[24]), "+f"(d[25]), "+f"(d[26]), "+f"(d[27]), "+f"(d[28]), "+f"(d[29]), "+f"(d[30]), "+f"(d[31]), "+f"(d[32]), "+f"(d[33]), "+f"(d[34]), "+f"(d[35]), "+f"(d[36]), "+f"(d[37]), "+f"(d[38]), "+f"(d[39]), "+f"(d[40]), "+f"(d[41]), "+f"(d[42]), "+f"(d[43]), "+f"(d[44]), "+f"(d[45]), "+f"(d[46]), "+f"(d[47]), "+f"(d[48]), "+f"(d[49]), "+f"(d[50]), "+f"(d[51]), "+f"(d[52]), "+f"(d[53]), "+f"(d[54]), "+f"(d[55]), "+f"(d[56]), "+f"(d[57]), "+f"(d[58]), "+f"(d[59]), "+f"(d[60]), "+f"(d[61]), "+f"(d[62]), "+f"(d[63]), "+f"(d[64]), "+f"(d[65]), "+f"(d[66]), "+f"(d[67]), "+f"(d[68]), "+f"(d[69]), "+f"(d[70]), "+f"(d[71]), "+f"(d[72]), "+f"(d[73]), "+f"(d[74]), "+f"(d[75]), "+f"(d[76]), "+f"(d[77]), "+f"(d[78]), "+f"(d[79]), "+f"(d[80]), "+f"(d[81]), "+f"(d[82]), "+f"(d[83]), "+f"(d[84]), "+f"(d[85]), "+f"(d[86]), "+f"(d[87]), "+f"(d[88]), "+f"(d[89]), "+f"(d[90]), "+f"(d[91]), "+f"(d[92]), "+f"(d[93]), "+f"(d[94]), "+f"(d[95])
               : "r"(da), "r"(db), "n"(scale_d));
#undef R_
}
template <int scale_d> __device__ __forceinline__ void wgmma4_n128(float* d, uint32_t da, uint32_t db) {
#define R_ "{%0,%1,%2,%3,%4,%5,%6,%7,%8,%9,%10,%11,%12,%13,%14,%15,%16,%17,%18,%19,%20,%21,%22,%23,%24,%25,%26,%27,%28,%29,%30,%31,%32,%33,%34,%35,%36,%37,%38,%39,%40,%41,%42,%43,%44,%45,%46,%47,%48,%49,%50,%51,%52,%53,%54,%55,%56,%57,%58,%59,%60,%61,%62,%63}"
  asm volatile("{\n.reg .pred p, q;\n.reg .b64 a, b;\nsetp.ne.b32 p, %66, 0;\nsetp.eq.b32 q, 0, 0;\nmov.b64 a, {%64, 0x40000040};\nmov.b64 b, {%65, 0x40000040};\n"
               "wgmma.mma_async.sync.aligned.m64n128k16.f32.bf16.bf16 " R_ ", a, b, p, 1, 1, 0, 1;\nadd.s64 a, a, 2;\nadd.s64 b, b, 128;\n"
               "wgmma.mma_async.sync.aligned.m64n128k16.f32.bf16.bf16 " R_ ", a, b, q, 1, 1, 0, 1;\nadd.s64 a, a, 2;\nadd.s64 b, b, 128;\n"
               "wgmma.mma_async.sync.aligned.m64n128k16.f32.bf16.bf16 " R_ ", a, b, q, 1, 1, 0, 1;\nadd.s64 a, a, 2;\nadd.s64 b, b, 128;\n"
               "wgmma.mma_async.sync.aligned.m64n128k16.f32.bf16.bf16 " R_ ", a, b, q, 1, 1, 0, 1;\n}\n"
               : "+f"(d[0]), "+f"(d[1]), "+f"(d[2]), "+f"(d[3]), "+f"(d[4]), "+f"(d[5]), "+f"(d[6]), "+f"(d[7]), "+f"(d[8]), "+f"(d[9]), "+f"(d[10]), "+f"(d[11]), "+f"(d[12]), "+f"(d[13]), "+f"(d[14]), "+f"(d[15]), "+f"(d[16]), "+f"(d[17]), "+f"(d[18]), "+f"(d[19]), "+f"(d[20]), "+f"(d[21]), "+f"(d[22]), "+f"(d[23]), "+f"(d[24]), "+f"(d[25]), "+f"(d[26]), "+f"(d[27]), "+f"(d[28]), "+f"(d[29]), "+f"(d[30]), "+f"(d[31]), "+f"(d[32]), "+f"(d[33]), "+f"(d[34]), "+f"(d[35]), "+f"(d[36]), "+f"(d[37]), "+f"(d[38]), "+f"(d[39]), "+f"(d[40]), "+f"(d[41]), "+f"(d[42]), "+f"(d[43]), "+f"(d[44]), "+f"(d[45]), "+f"(d[46]), "+f"(d[47]), "+f"(d[48]), "+f"(d[49]), "+f"(d[50]), "+f"(d[51]), "+f"(d[52]), "+f"(d[53]), "+f"(d[54]), "+f"(d[55]), "+f"(d[56]), "+f"(d[57]), "+f"(d[58]), "+f"(d[59]), "+f"(d[60]), "+f"(d[61]), "+f"(d[62]), "+f"(d[63])
               : "r"(da), "r"(db), "n"(scale_d));
#undef R_
}
template <int scale_d> __device__ __forceinline__ void wgmma_n32(float* d, uint64_t descA, uint64_t descB) {
  asm volatile("{\n.reg .pred p;\nsetp.ne.b32 p, %18, 0;\n"
               "wgmma.mma_async.sync.aligned.m64n32k16.f32.bf16.bf16 {%0,%1,%2,%3,%4,%5,%6,%7,%8,%9,%10,%11,%12,%13,%14,%15}, %16, %17, p, 1, 1, 0, 1;\n}\n"
               : "+f"(d[0]), "+f"(d[1]), "+f"(d[2]), "+f"(d[3]), "+f"(d[4]), "+f"(d[5]), "+f"(d[6]), "+f"(d[7]), "+f"(d[8]), "+f"(d[9]), "+f"(d[10]), "+f"(d[11]), "+f"(d[12]), "+f"(d[13]), "+f"(d[14]), "+f"(d[15])
               : "l"(descA), "l"(descB), "n"(scale_d));
}
template <int scale_d, int tnsp_a> __device__ __forceinline__ void wgmma_n40(float* d, uint64_t descA, uint64_t descB) {
  asm volatile("{\n.reg .pred p;\nsetp.ne.b32 p, %22, 0;\n"
               "wgmma.mma_async.sync.aligned.m64n40k16.f32.bf16.bf16 {%0,%1,%2,%3,%4,%5,%6,%7,%8,%9,%10,%11,%12,%13,%14,%15,%16,%17,%18,%19}, %20, %21, p, 1, 1, %23, 1;\n}\n"
               : "+f"(d[0]), "+f"(d[1]), "+f"(d[2]), "+f"(d[3]), "+f"(d[4]), "+f"(d[5]), "+f"(d[6]), "+f"(d[7]), "+f"(d[8]), "+f"(d[9]), "+f"(d[10]), "+f"(d[11]), "+f"(d[12]), "+f"(d[13]), "+f"(d[14]), "+f"(d[15]), "+f"(d[16]), "+f"(d[17]), "+f"(d[18]), "+f"(d[19])
               : "l"(descA), "l"(descB), "n"(scale_d), "n"(tnsp_a));
}
template <int scale_d> __device__ __forceinline__ void wgmma_n40_rs(float* d, const uint32_t* a, uint64_t descB) {
  asm volatile("{\n.reg .pred p;\nsetp.ne.b32 p, %25, 0;\n"
               "wgmma.mma_async.sync.aligned.m64n40k16.f32.bf16.bf16 {%0,%1,%2,%3,%4,%5,%6,%7,%8,%9,%10,%11,%12,%13,%14,%15,%16,%17,%18,%19}, {%20,%21,%22,%23}, %24, p, 1, 1, 1;\n}\n"
               : "+f"(d[0]), "+f"(d[1]), "+f"(d[2]), "+f"(d[3]), "+f"(d[4]), "+f"(d[5]), "+f"(d[6]), "+f"(d[7]), "+f"(d[8]), "+f"(d[9]), "+f"(d[10]), "+f"(d[11]), "+f"(d[12]), "+f"(d[13]), "+f"(d[14]), "+f"(d[15]), "+f"(d[16]), "+f"(d[17]), "+f"(d[18]), "+f"(d[19])
               : "r"(a[0]), "r"(a[1]), "r"(a[2]), "r"(a[3]), "l"(descB), "n"(scale_d));
}
__device__ __forceinline__ void wgmma_copy(float* d, uint32_t da, uint64_t descB) {
  asm volatile("{\n.reg .pred p;\n.reg .b64 a;\nsetp.ne.b32 p, 0, 0;\nmov.b64 a, {%64, 0x40000040};\n"
               "wgmma.mma_async.sync.aligned.m64n16k16.f32.bf16.bf16 {%0,%1,%2,%3,%4,%5,%6,%7}, a, %65, p, 1, 1, 0, 0;\nadd.s64 a, a, 2;\n"
               "wgmma.mma_async.sync.aligned.m64n16k16.f32.bf16.bf16 {%8,%9,%10,%11,%12,%13,%14,%15}, a, %65, p, 1, 1, 0, 0;\nadd.s64 a, a, 2;\n"
               "wgmma.mma_async.sync.aligned.m64n16k16.f32.bf16.bf16 {%16,%17,%18,%19,%20,%21,%22,%23}, a, %65, p, 1, 1, 0, 0;\nadd.s64 a, a, 2;\n"
               "wgmma.mma_async.sync.aligned.m64n16k16.f32.bf16.bf16 {%24,%25,%26,%27,%28,%29,%30,%31}, a, %65, p, 1, 1, 0, 0;\nadd.s64 a, a, 1018;\n"
               "wgmma.mma_async.sync.aligned.m64n16k16.f32.bf16.bf16 {%32,%33,%34,%35,%36,%37,%38,%39}, a, %65, p, 1, 1, 0, 0;\nadd.s64 a, a, 2;\n"
               "wgmma.mma_async.sync.aligned.m64n16k16.f32.bf16.bf16 {%40,%41,%42,%43,%44,%45,%46,%47}, a, %65, p, 1, 1, 0, 0;\nadd.s64 a, a, 2;\n"
               "wgmma.mma_async.sync.aligned.m64n16k16.f32.bf16.bf16 {%48,%49,%50,%51,%52,%53,%54,%55}, a, %65, p, 1, 1, 0, 0;\nadd.s64 a, a, 2;\n"
               "wgmma.mma_async.sync.aligned.m64n16k16.f32.bf16.bf16 {%56,%57,%58,%59,%60,%61,%62,%63}, a, %65, p, 1, 1, 0, 0;\n"
               "}\n"
               : "+f"(d[0]), "+f"(d[1]), "+f"(d[2]), "+f"(d[3]), "+f"(d[4]), "+f"(d[5]), "+f"(d[6]), "+f"(d[7]), "+f"(d[8]), "+f"(d[9]), "+f"(d[10]), "+f"(d[11]), "+f"(d[12]), "+f"(d[13]), "+f"(d[14]), "+f"(d[15]), "+f"(d[16]), "+f"(d[17]), "+f"(d[18]), "+f"(d[19]), "+f"(d[20]), "+f"(d[21]), "+f"(d[22]), "+f"(d[23]), "+f"(d[24]), "+f"(d[25]), "+f"(d[26]), "+f"(d[27]), "+f"(d[28]), "+f"(d[29]), "+f"(d[30]), "+f"(d[31]), "+f"(d[32]), "+f"(d[33]), "+f"(d[34]), "+f"(d[35]), "+f"(d[36]), "+f"(d[37]), "+f"(d[38]), "+f"(d[39]), "+f"(d[40]), "+f"(d[41]), "+f"(d[42]), "+f"(d[43]), "+f"(d[44]), "+f"(d[45]), "+f"(d[46]), "+f"(d[47]), "+f"(d[48]), "+f"(d[49]), "+f"(d[50]), "+f"(d[51]), "+f"(d[52]), "+f"(d[53]), "+f"(d[54]), "+f"(d[55]), "+f"(d[56]), "+f"(d[57]), "+f"(d[58]), "+f"(d[59]), "+f"(d[60]), "+f"(d[61]), "+f"(d[62]), "+f"(d[63])
               : "r"(da), "l"(descB));
}
template <int scale_d> __device__ __forceinline__ void wgmma_n192_rs(float* d, const uint32_t* a, uint32_t db) {
  asm volatile("{\n.reg .pred p;\n.reg .b64 b;\nsetp.ne.b32 p, %101, 0;\nmov.b64 b, {%100, 0x40000040};\n"
               "wgmma.mma_async.sync.aligned.m64n192k16.f32.bf16.bf16 {%0,%1,%2,%3,%4,%5,%6,%7,%8,%9,%10,%11,%12,%13,%14,%15,%16,%17,%18,%19,%20,%21,%22,%23,%24,%25,%26,%27,%28,%29,%30,%31,%32,%33,%34,%35,%36,%37,%38,%39,%40,%41,%42,%43,%44,%45,%46,%47,%48,%49,%50,%51,%52,%53,%54,%55,%56,%57,%58,%59,%60,%61,%62,%63,%64,%65,%66,%67,%68,%69,%70,%71,%72,%73,%74,%75,%76,%77,%78,%79,%80,%81,%82,%83,%84,%85,%86,%87,%88,%89,%90,%91,%92,%93,%94,%95}, {%96,%97,%98,%99}, b, p, 1, 1, 1;\n}\n"
               : "+f"(d[0]), "+f"(d[1]), "+f"(d[2]), "+f"(d[3]), "+f"(d[4]), "+f"(d[5]), "+f"(d[6]), "+f"(d[7]), "+f"(d[8]), "+f"(d[9]), "+f"(d[10]), "+f"(d[11]), "+f"(d[12]), "+f"(d[13]), "+f"(d[14]), "+f"(d[15]), "+f"(d[16]), "+f"(d[17]), "+f"(d[18]), "+f"(d[19]), "+f"(d[20]), "+f"(d[21]), "+f"(d[22]), "+f"(d[23]), "+f"(d[24]), "+f"(d[25]), "+f"(d[26]), "+f"(d[27]), "+f"(d[28]), "+f"(d[29]), "+f"(d[30]), "+f"(d[31]), "+f"(d[32]), "+f"(d[33]), "+f"(d[34]), "+f"(d[35]), "+f"(d[36]), "+f"(d[37]), "+f"(d[38]), "+f"(d[39]), "+f"(d[40]), "+f"(d[41]), "+f"(d[42]), "+f"(d[43]), "+f"(d[44]), "+f"(d[45]), "+f"(d[46]), "+f"(d[47]), "+f"(d[48]), "+f"(d[49]), "+f"(d[50]), "+f"(d[51]), "+f"(d[52]), "+f"(d[53]), "+f"(d[54]), "+f"(d[55]), "+f"(d[56]), "+f"(d[57]), "+f"(d[58]), "+f"(d[59]), "+f"(d[60]), "+f"(d[61]), "+f"(d[62]), "+f"(d[63]), "+f"(d[64]), "+f"(d[65]), "+f"(d[66]), "+f"(d[67]), "+f"(d[68]), "+f"(d[69]), "+f"(d[70]), "+f"(d[71]), "+f"(d[72]), "+f"(d[73]), "+f"(d[74]), "+f"(d[75]), "+f"(d[76]), "+f"(d[77]), "+f"(d[78]), "+f"(d[79]), "+f"(d[80]), "+f"(d[81]), "+f"(d[82]), "+f"(d[83]), "+f"(d[84]), "+f"(d[85]), "+f"(d[86]), "+f"(d[87]), "+f"(d[88]), "+f"(d[89]), "+f"(d[90]), "+f"(d[91]), "+f"(d[92]), "+f"(d[93]), "+f"(d[94]), "+f"(d[95])
               : "r"(a[0]), "r"(a[1]), "r"(a[2]), "r"(a[3]), "r"(db), "n"(scale_d));
}
__device__ __forceinline__ uint64_t make_desc(uint32_t addr, uint32_t lbo_bytes, uint32_t sbo_bytes) {
  return (uint64_t)((addr & 0x3FFFF) >> 4) | ((uint64_t)(lbo_bytes >> 4) << 16) | ((uint64_t)(sbo_bytes >> 4) << 32) | (1ull << 62);
}

__device__ __forceinline__ void ldsm_x4(uint32_t addr, uint32_t& r0, uint32_t& r1, uint32_t& r2, uint32_t& r3) {
  asm volatile("ldmatrix.sync.aligned.m8n8.x4.shared.b16 {%0,%1,%2,%3}, [%4];" : "=r"(r0), "=r"(r1), "=r"(r2), "=r"(r3) : "r"(addr) : "memory");
}
__device__ __forceinline__ void ldsm_x4_t(uint32_t addr, uint32_t& r0, uint32_t& r1, uint32_t& r2, uint32_t& r3) {
  asm volatile("ldmatrix.sync.aligned.m8n8.x4.trans.shared.b16 {%0,%1,%2,%3}, [%4];" : "=r"(r0), "=r"(r1), "=r"(r2), "=r"(r3) : "r"(addr) : "memory");
}
__device__ __forceinline__ void stsm_x4(uint32_t addr, uint32_t r0, uint32_t r1, uint32_t r2, uint32_t r3) {
  asm volatile("stmatrix.sync.aligned.m8n8.x4.shared.b16 [%0], {%1,%2,%3,%4};" :: "r"(addr), "r"(r0), "r"(r1), "r"(r2), "r"(r3) : "memory");
}
__device__ __forceinline__ void stsm_x4_t(uint32_t addr, uint32_t r0, uint32_t r1, uint32_t r2, uint32_t r3) {
  asm volatile("stmatrix.sync.aligned.m8n8.x4.trans.shared.b16 [%0], {%1,%2,%3,%4};" :: "r"(addr), "r"(r0), "r"(r1), "r"(r2), "r"(r3) : "memory");
}
__device__ __forceinline__ void sts128(uint32_t addr, uint32_t a, uint32_t b, uint32_t c, uint32_t d) {
  asm volatile("st.shared.v4.u32 [%0], {%1,%2,%3,%4};" :: "r"(addr), "r"(a), "r"(b), "r"(c), "r"(d) : "memory");
}
__device__ __forceinline__ float lds32f(uint32_t addr) {
  float v;
  asm volatile("ld.shared.f32 %0, [%1];" : "=f"(v) : "r"(addr) : "memory");
  return v;
}
__device__ __forceinline__ void sts32f(uint32_t addr, float a) {
  asm volatile("st.shared.f32 [%0], %1;" :: "r"(addr), "f"(a) : "memory");
}
__device__ __forceinline__ void mma_bf16(float (&c)[4], uint32_t a0, uint32_t a1, uint32_t a2, uint32_t a3, uint32_t b0, uint32_t b1) {
  asm volatile("mma.sync.aligned.m16n8k16.row.col.f32.bf16.bf16.f32 {%0,%1,%2,%3}, {%4,%5,%6,%7}, {%8,%9}, {%0,%1,%2,%3};"
               : "+f"(c[0]), "+f"(c[1]), "+f"(c[2]), "+f"(c[3]) : "r"(a0), "r"(a1), "r"(a2), "r"(a3), "r"(b0), "r"(b1));
}
__device__ __forceinline__ void mma_bf16_z(float (&c)[4], uint32_t a0, uint32_t a1, uint32_t a2, uint32_t a3, uint32_t b0, uint32_t b1) {
  asm volatile("mma.sync.aligned.m16n8k16.row.col.f32.bf16.bf16.f32 {%0,%1,%2,%3}, {%4,%5,%6,%7}, {%8,%9}, {%10,%10,%10,%10};"
               : "=f"(c[0]), "=f"(c[1]), "=f"(c[2]), "=f"(c[3]) : "r"(a0), "r"(a1), "r"(a2), "r"(a3), "r"(b0), "r"(b1), "f"(0.f));
}
__device__ __forceinline__ uint32_t movm_t(uint32_t v) {
  uint32_t r;
  asm volatile("movmatrix.sync.aligned.m8n8.trans.b16 %0, %1;" : "=r"(r) : "r"(v));
  return r;
}
__device__ __forceinline__ uint32_t pack_bf16(float lo, float hi) {
  uint32_t r;
  asm("cvt.rn.bf16x2.f32 %0, %1, %2;" : "=r"(r) : "f"(hi), "f"(lo));
  return r;
}
__device__ __forceinline__ float bf_lo(uint32_t v) { return __uint_as_float(v << 16); }
__device__ __forceinline__ float bf_hi(uint32_t v) { return __uint_as_float(v & 0xFFFF0000u); }
__device__ __forceinline__ void split3(float x, uint32_t& h, uint32_t& m, uint32_t& l) {
  h = pack_bf16(x, 0.f); x -= bf_lo(h);
  m = pack_bf16(x, 0.f); x -= bf_lo(m);
  l = pack_bf16(x, 0.f);
}
__device__ __forceinline__ float ex2(float x) { float r; asm("ex2.approx.ftz.f32 %0, %1;" : "=f"(r) : "f"(x)); return r; }
__device__ __forceinline__ float rcp_fast(float x) { float r; asm("rcp.approx.ftz.f32 %0, %1;" : "=f"(r) : "f"(x)); return r; }
__device__ __forceinline__ void red_v4(float* p, float a, float b, float c, float d) {
  asm volatile("red.global.add.v4.f32 [%0], {%1, %2, %3, %4};" :: "l"(p), "f"(a), "f"(b), "f"(c), "f"(d) : "memory");
}
__device__ __forceinline__ uint4 ld_ll(const uint4* p) {
  uint4 v;
  asm volatile("{\n.reg .b64 a, b;\nld.relaxed.gpu.global.v2.b64 {a, b}, [%4];\nmov.b64 {%0, %1}, a;\nmov.b64 {%2, %3}, b;\n}\n"
               : "=r"(v.x), "=r"(v.y), "=r"(v.z), "=r"(v.w) : "l"(p) : "memory");
  return v;
}
__device__ __forceinline__ void st_b64(uint2* p, uint32_t a, uint32_t b) {
  asm volatile("{\n.reg .b64 v;\nmov.b64 v, {%1, %2};\nst.relaxed.gpu.global.b64 [%0], v;\n}\n" :: "l"(p), "r"(a), "r"(b) : "memory");
}
__device__ __forceinline__ void st_b128(uint4* p, uint32_t a, uint32_t b, uint32_t c, uint32_t d) {
  asm volatile("{\n.reg .b128 v;\nmov.b128 v, {%1, %2, %3, %4};\nst.relaxed.gpu.global.b128 [%0], v;\n}\n" :: "l"(p), "r"(a), "r"(b), "r"(c), "r"(d) : "memory");
}
__device__ __forceinline__ uint4 ld_b128(const uint4* p) {
  uint4 v;
  asm volatile("{\n.reg .b128 v;\nld.relaxed.gpu.global.b128 v, [%4];\nmov.b128 {%0, %1, %2, %3}, v;\n}\n" : "=r"(v.x), "=r"(v.y), "=r"(v.z), "=r"(v.w) : "l"(p) : "memory");
  return v;
}

constexpr float LOG2E = 1.4426950408889634f;

struct Params {
  const __nv_bfloat16* wA_o;
  const __nv_bfloat16* wB_qkv;
  const __nv_bfloat16* wB_o;
  const unsigned* epoch;
  __nv_bfloat16* out;
};

#define ACC_DEF(d, n) _Pragma("unroll") for (int i_ = 0; i_ < (n); i_++) asm volatile("" : "=f"(d[i_]))
#define ACC_FENCE(d, n) _Pragma("unroll") for (int i_ = 0; i_ < (n); i_++) asm volatile("" : "+f"(d[i_]) :: "memory")
#define PIN(a, n) _Pragma("unroll") for (int i_ = 0; i_ < (n); i_++) asm volatile("" : "+f"((a)[i_]))
#define PINU(a, n) _Pragma("unroll") for (int i_ = 0; i_ < (n); i_++) asm volatile("" : "+r"((a)[i_]))

#define V_ADDR(p0, sw) uint32_t va_[2] = {(p0) + (srowoff >> 1) + (lhi ^ lsw2 ^ (sw)), (p0) + (srowoff >> 1) + ((32 + lhi) ^ lsw2 ^ (sw))}
#define STAGE_V(acc) { \
    _Pragma("unroll") for (int j_ = 0; j_ < 4; j_++) { \
      const float* a_ = (acc) + j_ * 8; \
      stsm_x4(va_[j_ & 1] + (j_ >> 1) * 8192, \
              pack_bf16(rs0 * a_[0], rs0 * a_[1]), pack_bf16(rs1 * a_[2], rs1 * a_[3]), pack_bf16(rs0 * a_[4], rs0 * a_[5]), pack_bf16(rs1 * a_[6], rs1 * a_[7])); } }
#define FRAG(dst, acc, TR, grp) { \
    _Pragma("unroll") for (int i_ = 15; i_ >= 0; i_--) { \
      const float r_ = (i_ & 8) ? rs1 : rs0; \
      const uint32_t w_ = pack_bf16(r_ * (acc)[4 * (i_ & 7) + (i_ >> 3) * 2], r_ * (acc)[4 * (i_ & 7) + (i_ >> 3) * 2 + 1]); \
      (dst)[8 + i_] = (TR) ? movm_t(w_) : w_; \
      if (i_ == 8 && warp >= 6 && mm < 15) { \
        _Pragma("unroll") for (int j_ = 0; j_ < 2; j_++) \
          st_b128(g_halo + (size_t)(mm * 8 + jj) * 512 + ((grp) * 4 + warp * 2 - 12 + j_) * 32 + lane, ((dst)[16 + j_ * 4] & ~1u) | H_BIT(l), (dst)[17 + j_ * 4], (dst)[18 + j_ * 4], (dst)[19 + j_ * 4]); } } \
    PINU((dst) + 8, 16); }
#define FRAG_PUT(src, slot) if (warp < 6) { _Pragma("unroll") for (int j_ = 0; j_ < 2; j_++) \
      sts128(sbase + OFF_S + (slot) * 8192 + 2048 + warp * 1024 + j_ * 512 + lane * 16, (src)[j_ * 4], (src)[j_ * 4 + 1], (src)[j_ * 4 + 2], (src)[j_ * 4 + 3]); }
#define FRAG_GET(dst, slot) { _Pragma("unroll") for (int j_ = 0; j_ < 2; j_++) \
      asm volatile("ld.shared.v4.u32 {%0, %1, %2, %3}, [%4];" : "=r"((dst)[j_ * 4]), "=r"((dst)[j_ * 4 + 1]), "=r"((dst)[j_ * 4 + 2]), "=r"((dst)[j_ * 4 + 3]) \
                   : "r"(sbase + OFF_S + (slot) * 8192 + warp * 1024 + j_ * 512 + lane * 16) : "memory"); }
#define RW(j) (((j) >> 1) * 4 + ((j) & 1))
template <int POS> __device__ __forceinline__ float exps16_(float* o, const float* p) {
  float s[4];
#pragma unroll
  for (int j = 0; j < 16; j++) { o[j] = ex2(POS ? p[RW(j)] : -p[RW(j)]); if (j < 4) s[j] = o[j]; else s[j & 3] += o[j]; }
  const float r = (s[0] + s[1]) + (s[2] + s[3]);
  return r + __shfl_xor_sync(0xffffffffu, r, 1);
}
template <int POS> __device__ __forceinline__ void exps16_fix(float* o, const float* p, float& sum) {
  if (__builtin_expect(__any_sync(0xffffffffu, !(sum > SUMLO && sum < SUMHI)), 0)) {
    float m = p[0], q[32];
#pragma unroll
    for (int j = 1; j < 16; j++) m = POS ? fmaxf(m, p[RW(j)]) : fminf(m, p[RW(j)]);
    const float x = __shfl_xor_sync(0xffffffffu, m, 1);
    m = POS ? fmaxf(m, x) : fminf(m, x);
#pragma unroll
    for (int j = 0; j < 16; j++) q[RW(j)] = p[RW(j)] - m;
    sum = exps16_<POS>(o, q);
  }
}
__device__ __forceinline__ void store16(const float* e, float sum, uint32_t dst, uint32_t dsw, int c0) {
  const float inv = rcp_fast(sum);
#pragma unroll
  for (int j = 0; j < 2; j++)
    sts128(dst + (((c0 + j) << 4) ^ dsw), pack_bf16(e[j * 8] * inv, e[j * 8 + 1] * inv), pack_bf16(e[j * 8 + 2] * inv, e[j * 8 + 3] * inv),
           pack_bf16(e[j * 8 + 4] * inv, e[j * 8 + 5] * inv), pack_bf16(e[j * 8 + 6] * inv, e[j * 8 + 7] * inv));
}
template <int POS> __device__ __forceinline__ void expp16(uint32_t* o, float* p) {
  {
#pragma unroll
    for (int r = 0; r < 4; r += 2) {
      float m = p[r];
#pragma unroll
      for (int j = 1; j < 8; j++) m = POS ? fmaxf(m, p[r + RW(j)]) : fminf(m, p[r + RW(j)]);
#pragma unroll
      for (int s = 1; s <= 2; s <<= 1) { const float x = __shfl_xor_sync(0xffffffffu, m, s); m = POS ? fmaxf(m, x) : fminf(m, x); }
#pragma unroll
      for (int j = 0; j < 8; j++) p[r + RW(j)] -= m;
    }
  }
#pragma unroll
  for (int j = 0; j < 8; j++) o[j] = pack_bf16(ex2(POS ? p[2 * j] : -p[2 * j]), ex2(POS ? p[2 * j + 1] : -p[2 * j + 1]));
}
__device__ __forceinline__ void scale32(float* o, const float* p, float c0, float c1) {
#pragma unroll
  for (int i = 0; i < 32; i++) asm volatile("mul.f32 %0, %1, %2;" : "=f"(o[i]) : "f"(p[i]), "f"((i & 2) ? c1 : c0));
}
__device__ __forceinline__ bool any_big(const float* p) {
  float m[4];
#pragma unroll
  for (int i = 0; i < 32; i++) m[i >> 3] = (i & 7) ? fmaf(p[i], p[i], m[i >> 3]) : p[i] * p[i];
  return __any_sync(0xffffffffu, !(fmaxf(fmaxf(m[0], m[1]), fmaxf(m[2], m[3])) < BIGLIM));
}
__device__ __forceinline__ void phiq_a(float* p, bool big) {
  if (__builtin_expect(!big, 1)) {
#pragma unroll
    for (int j = 0; j < 16; j++) p[j] = ex2(p[j]);
  }
}
template <int NEXT> __device__ __forceinline__ void phiq_b(uint32_t* o, float* p, bool big) {
  if (__builtin_expect(big, 0)) {
    expp16<0>(o, p); expp16<1>(o + 8, p);
  } else {
    if (NEXT) phiq_a(p + 16, false);
#pragma unroll
    for (int j = 0; j < 4; j++) {
      const float a = p[4 * j], b = p[4 * j + 1], c = p[4 * j + 2], d = p[4 * j + 3];
      const float ab = a * b, cd = c * d, r = rcp_fast(ab * cd), x = r * cd, y = r * ab;
      o[2 * j] = pack_bf16(x * b, x * a); o[2 * j + 1] = pack_bf16(y * d, y * c);
      o[8 + 2 * j] = pack_bf16(a, b); o[9 + 2 * j] = pack_bf16(c, d);
    }
  }
}
#define SCHED_FENCE() asm volatile("pmevent 0;" ::: "memory")

__global__ void __cluster_dims__(2, 1, 1) __launch_bounds__(384, 1)
mega_kernel(const Params prm  , const __grid_constant__ CUtensorMap tm_x0, const __grid_constant__ CUtensorMap tm_os,
            const __grid_constant__ CUtensorMap tm_o, const __grid_constant__ CUtensorMap tm_wf,
            const __grid_constant__ CUtensorMap tm_wqA, const __grid_constant__ CUtensorMap tm_wqB,
            const __grid_constant__ CUtensorMap tm_woA, const __grid_constant__ CUtensorMap tm_woB,
            const __grid_constant__ CUtensorMap tm_phi) {
  extern __shared__ __align__(1024) uint8_t smem_raw[];
  const uint32_t sbase = smem_u32(smem_raw);
  const uint32_t bar_full = sbase + OFF_BAR;
  const uint32_t bar_done = bar_full + 384;
  const uint32_t bar_stat = bar_full + 768, bar_stat2 = bar_full + 776, bar_epi = bar_full + 784, bar_phi = bar_full + 936  , bar_halo = bar_full + 904  ;
  const uint32_t bar_xr = bar_full + 800, bar_lx = bar_full + 808, bar_stg = bar_full + 832;
  const uint32_t bar_chk = bar_full + 848;

  const int warp = __shfl_sync(0xffffffffu, threadIdx.x >> 5, 0), lane = threadIdx.x & 31;
  const uint32_t bar_kx = sbase + OFF_ID + 384 + warp * 8;
  uint32_t rank;
  asm volatile("mov.u32 %0, %%cluster_ctarank;" : "=r"(rank));
  const int aux = (int)blockIdx.x - NMAIN, tp = (int)(blockIdx.x >> 1) - 4;
  const int gp = tp < 0 ? 0 : (tp < 32 ? tp & 7 : 1 + (tp - 32) % 7), me = tp < 0 ? tp + 8 : (tp < 32 ? tp >> 3 : 4 + (tp - 32) / 7);
  const int jj = me, cc = gp;
  const int cta = aux >= 0 ? -1 : (cc * 8 + jj) * 2 + (int)rank;
  const int mm = cc * 2 + (int)rank;

#define LOAD_EPOCH() const unsigned epoch = ld_relaxed(prm.epoch), ep1 = epoch + 1; (void)epoch
  int budget = 1 << 22;
  unsigned epoch0 = 0;

  if (cta >= 0) {
    if (warp >= 8 && warp < 10 && elect_one()) {
      const int u = warp - 8;
      const uint32_t fb = bar_full + u * 8;
      mbar_init(fb, 1);
      asm volatile("fence.mbarrier_init.release.cluster;" ::: "memory");
      fence_proxy_async_smem();
      mbar_expect_tx(fb, QST + SLOT);
      if (STAG2 && u) __nanosleep(STAG2);
      tma_load_t(sbase + OFF_RA + u * SLOT, &tm_x0, fb, srcb(jj, u) * 128, mm * 128);
#pragma unroll
      for (int i = 0; i < 6; i++) tma_load_2d(sbase + u * QST + i * 4096, &tm_wqA, fb, jj * 128 + (i >> 1) * 1024, srcb(jj, u) * 128 + (i & 1) * 32);
      PROFT(472 + u);
    }
    __syncwarp();
    if (elect_one()) {
#pragma unroll
      for (int i = 0; i < 4; i++) {
        const int u = warp * 4 + i;
        mbar_init(u < 2 ? bar_kx : bar_full + u * 8, ((u >= 4 && u < 11) || (u > 32 && u != 40)) ? 2 : 1); mbar_init(bar_done + u * 8, 16);
      }
      mbar_init(bar_stat + warp * 16, 0x111111181182ull >> (4 * warp) & 15);
      mbar_init(bar_stat + warp * 16 + 8, 0x111111121811ull >> (4 * warp) & 15);
      mbar_init(bar_chk + 112 + (warp & 7) * 8, 1);
      mbar_init(bar_kx, 1);
      asm volatile("fence.mbarrier_init.release.cluster;" ::: "memory");
    }
    __syncwarp();
    if (threadIdx.x == 383) epoch0 = ld_relaxed(prm.epoch);
    if (PRL == 0 && lane == 0 && warp >= 8) PROFT(440 + warp - 8);
    __syncthreads();
    if (PRL == 0 && threadIdx.x == 256) PROFT(444);
    asm volatile("barrier.cluster.arrive.relaxed.aligned;" ::: "memory");
  }

  if (cta < 0) {
    LOAD_EPOCH();
    const uint32_t buf = sbase + warp * SLOT, bar = sbase + OFF_BAR + warp * 16;
    const uint32_t lsw = (lane & 7) << 4, lhi = (lane >> 4) << 4, lrow = (lane & 15) * 128;
    const bool el = elect_one();
    if (el) {
      mbar_init(bar, 1); mbar_init(bar + 8, 1);
      asm volatile("fence.mbarrier_init.release.cluster;" ::: "memory");
    }
#pragma unroll 1
    for (int rd = 0; rd < (NLAYERS > 1 ? 5 : 2); rd++) {
      if (rd >= 2 && warp >= 8) break;
      const int tk = rd < 2 ? aux * 12 + warp : aux * 8 + warp;
      const int half = tk & 1;
      const int blk = rd < 2 ? (tk >> 1) * 2 + rd : (4 - rd) * 16 + (tk >> 1);
      const CUtensorMap* tm = rd < 2 ? &tm_wqA : (rd == 2 ? &tm_wqB : &tm_wf);
      const int j0 = (blk & 15) >> 1;
#define AUX_LOAD(n) { const uint32_t d_ = buf + ((n) & 1) * 8192, b_ = bar + ((n) & 1) * 8; const int r_ = kslice(j0, 2 * ((AUXORD >> (4 * (n))) & 7) + half) * 64; \
        mbar_expect_tx(b_, 8192); tma_load_2d(d_, tm, b_, blk * 64, r_); tma_load_2d(d_ + 4096, tm, b_, blk * 64, r_ + 32); }
      if (el) {
        if (rd == 3) { wait_flag(&g_flags.wfready[j0].v, ep1 * 16); fence_proxy_async_global(); }
        AUX_LOAD(0); AUX_LOAD(1);
      }
      __syncwarp();
      float cs[8][4];
#pragma unroll
      for (int i = 0; i < 8; i++) cs[i][0] = cs[i][1] = cs[i][2] = cs[i][3] = 0.f;
#pragma unroll 1
      for (int n = 0; n < 8; n++) {
        const uint32_t tb = buf + (n & 1) * 8192 + lrow;
        mbar_wait(bar + (n & 1) * 8, (n >> 1) & 1);
#pragma unroll
        for (int i = 0; i < 16; i++) {
          uint32_t b0, b1, b2, b3;
          ldsm_x4_t(tb + (i >> 2) * 2048 + (((i & 3) * 32 + lhi) ^ lsw), b0, b1, b2, b3);
          mma_bf16(cs[2 * (i & 3)], 0x3F803F80u, 0x3F803F80u, 0x3F803F80u, 0x3F803F80u, b0, b1);
          mma_bf16(cs[2 * (i & 3) + 1], 0x3F803F80u, 0x3F803F80u, 0x3F803F80u, 0x3F803F80u, b2, b3);
        }
        __syncwarp();
        if (el && n < 6) AUX_LOAD(n + 2);
        __syncwarp();
      }
      if (lane < 4) {
#pragma unroll
        for (int i = 0; i < 8; i++) st_b64(&g_colsum[rd >= 2][blk * 32 + i * 4 + lane][half], __float_as_uint(cs[i][0]), (__float_as_uint(cs[i][1]) & ~3u) | (ep1 & 3));
      }
      __syncwarp();
    }
  } else if (warp >= 8) {
    asm volatile("setmaxnreg.dec.sync.aligned.u32 40;");
    if (warp == 8) {
      const bool el = elect_one();
      cluster_wait();
      if (el) {
        if (PRL == 0) PROFT(445);
#pragma unroll 1
        for (int l = 0; l < NLAYERS; l++) {
          const uint32_t par = l & 1;
          const CUtensorMap* tqk = par ? &tm_wf : &tm_wqA;
          const CUtensorMap* tv = par ? &tm_wqB : &tm_wqA;
          const CUtensorMap* two = par ? &tm_woB : &tm_woA;
          if (l == 1) { LOAD_EPOCH(); wait_flag(&g_flags.wfready[jj].v, ep1 * 16); fence_proxy_async_global(); }
#pragma unroll 1
          for (int u = l ? 0 : EARLY; u < 32; u++) {
            const uint32_t fb = bar_full + u * 8;
            const int v = (l || u > 7) ? u : u - 4;
            const bool res = u < 11 || (u >= 18 && u < 22);
            mbar_expect_tx(fb, res ? QST : QST + SLOT);
            const int row = kslice(jj, v < 4 ? v & 1 : (u < 18 ? u - 2 : (u < 22 ? u - 6 : u - 20))) * 64 + (int)rank * 32;
            const int ps = v < 4 ? v >> 1 : (u >= 18), col = jj * 128 + ps * 64;
            const int c0 = par ? jj * 128 + (ps ? 0 : 1024) : col;
            const uint32_t dst = sbase + (u & 3) * QST + rank * 4096;
            uint32_t op[7] = {dst, dst + 8192, dst + 16384, (uint32_t)c0, (uint32_t)(c0 + (par ? 64 : 1024)), (uint32_t)(col + 2048), (uint32_t)row};
            PINU(op, 7);
            mbar_wait_sl(bar_done + (u >= 4 ? u - 4 : 43 + u + (u >> 1)) * 8, par ^ (u < 4));
            tma_load_2d_mc(op[0], tqk, fb, op[3], op[6]);
            tma_load_2d_mc(op[1], tqk, fb, op[4], op[6]);
            tma_load_2d_mc(op[2], tv, fb, op[5], op[6]);

            if (u < 8) PROFL3(472 + u);
          }
#pragma unroll 1
          for (int s = 0; s < 16; s++) {
            const uint32_t fb = bar_full + (32 + s) * 8;
            const int ts = s + 1;
            const bool ot = s >= 5 && ts < 8;
            mbar_expect_tx(fb, SLOT);
            uint32_t op[4] = {sbase + rank * 8192 + (uint32_t)((WO_BSLOT >> (4 * s)) & 15) * SLOT, (uint32_t)wslice(jj, s) * 64,
                              sbase + (uint32_t)((WO_ASLOT(par) >> (4 * ts)) & 15) * SLOT, (uint32_t)wslice(jj, ts) * 64};
            PINU(op, 4);
            mbar_wait_sl(bar_done + (28 + (uint32_t)((0xDCCBA98765433110ull >> (4 * s)) & 15)) * 8, par);
            tma_load_2d_mc(op[0], two, fb, jj * 128 + (int)rank * 64, op[1]);
            if (ot) {
              mbar_expect_tx(bar_chk - 8 + ts * 8, SLOT);
              tma_load_t(op[2], &tm_o, bar_chk - 8 + ts * 8, op[3], mm * 128);
            }
          }
        }
      }
      __syncwarp();
    } else if (warp == 9) {
      const bool el = elect_one();
      if (el) {
#pragma unroll
        for (int i = 0; i < 2; i++) {
          mbar_expect_tx(bar_full + 32 + i * 8, SLOT);
          mbar_wait_sl(bar_full + (i ? OWNW1 : OWNW0) * 8, 0);
          tma_load_t(sbase + OFF_S + i * SLOT, &tm_x0, bar_full + 32 + i * 8, jj * 128 + i * 64, mm * 128);
        }
      }
      __syncwarp();
      LOAD_EPOCH();
#pragma unroll 1
      for (int lp = 0; lp < 4 * NLAYERS; lp++) {
        const int l = lp >> 2, ph = lp & 3;
        if (ph == 3) continue;
        const uint32_t par = l & 1;
        const unsigned* pp = reinterpret_cast<const unsigned*>(g_obuf + (ph >> 1) * 64 + (size_t)(mm * 128 + (ph ? 0 : S_LEN) + ((lane & 7) | PROWS) * 16 + (jj & 1) * 8) * D_MODEL +
                                                               (jj >> 1) * 16 + srcb(jj, lane >> 3) * 128);
        const CUtensorMap* tm = lp ? &tm_o : &tm_x0;
        const int row = mm * 128 + ((ph || !l) ? 0 : S_LEN);
        const uint32_t bit = ph ? O_BIT(l) : X_BIT(l - 1);
        const uint32_t slots = ph ? (uint32_t)(WO_ASLOT(par) >> (ph * 32 - 28)) : 0x8769876u;
        const unsigned long long fr = ph == 0 ? XPACE : ph == 1 ? (par ? FRB : 0x35351F1E1Dull) : 0x27262524232232ull;
        uint32_t no = (lp == 0 || (lp & 7) == 1) ? 0 : (ph == 1 ? NOB : (ph ? NO1 : NOX)), v0 = 0, v1 = 0;
        mbar_wait_sl(ph ? bar_done + ((uint32_t)fr & 63) * 8 : (l ? bar_done + 47 * 8 : bar_full), ph ? par : (l ? par ^ 1 : 0));
        if (el && ph) PROFT(324 + l * 16 + ph);
        __syncwarp();
        if (no && (ph == 1 ? SPD1 : (ph ? SPD2 : SPD0))) __nanosleep(ph == 1 ? SPD1 : (ph ? SPD2 : SPD0));
        if (no) { v0 = ld_relaxed(pp); if (ph != 1) __nanosleep(POLLGAP); v1 = ld_relaxed(pp); }
#pragma unroll 1
        for (int i = lp ? 0 : 4; i < (ph == 1 ? 5 : 7); i++, no >>= 8) {
          uint32_t op[4] = {(lp ? bar_chk + (ph >> 1) * 112 : bar_full + 32) + i * 8  , sbase + ((slots >> (4 * i)) & 15) * SLOT,
                            (uint32_t)(srcb(jj, i) * 128 + (ph >> 1) * 64), bar_done + ((uint32_t)(fr >> (8 * i)) & 63) * 8};
          PINU(op, 4);
          if (el) mbar_expect_tx(op[0], SLOT);
#pragma unroll 1
          for (int it = 0; (no & 0xFF) && it < (1 << 18); it++) {
            no &= __ballot_sync(0xffffffffu, (v0 ^ bit) & 1) >> (8 * i);
            if (no) v0 = ld_relaxed(pp);
            if (!(no & 0xFF)) break;
            no &= __ballot_sync(0xffffffffu, (v1 ^ bit) & 1) >> (8 * i);
            if (no) v1 = ld_relaxed(pp);
          }
          if (i >= (ph ? 1 : 4)) mbar_wait_sl(op[3], par);
          if (el) {
            if (i == 0) PROFT(320 + l * 16 + ph);
            PROFL3(448 + ph * 8 + i);
            tma_load_t(op[1], tm, op[0], op[2], row);
          }
          __syncwarp();
        }
        if (ph == 0 && el) {
          if (l) { wait_flag(&g_flags.xready[l][mm].v, ep1 * 8); fence_proxy_async_global(); }
#pragma unroll 1
          for (int u = 11; u < 34; u++) {
            if (u == 18) u = 22;
            if (u == 32) mbar_expect_tx(bar_xr, 2 * SLOT);
            uint32_t op[3] = {sbase + OFF_RA + (u & 3) * SLOT, u < 32 ? bar_full + u * 8 : bar_xr, (uint32_t)kslice(jj, u < 18 ? u - 2 : (u < 32 ? u - 20 : u - 32)) * 64};
            PINU(op, 3);
            mbar_wait_sl(bar_done + (u - 4) * 8, par);
            tma_load_t(op[0], tm, op[1], op[2], row);
          }
        }
        __syncwarp();
      }
      if (el && atomicAdd(&g_flags.done.v, 1) == ep1 * NMAIN - 1) asm volatile("st.relaxed.gpu.global.u32 [%0], %1;" :: "l"(&g_flags.epoch.v), "r"(ep1) : "memory");
      __syncwarp();
      cluster_wait();
    } else {
      const int hw = warp - 10;
      if (elect_one()) {
        const uint32_t fb = bar_full + 16 + hw * 8;
        mbar_expect_tx(fb, QST + SLOT);
#pragma unroll
        for (int i = 0; i < 6; i++) tma_load_2d(sbase + (2 + hw) * QST + i * 4096, &tm_wqA, fb, jj * 128 + (i >> 1) * 1024, srcb(jj, 2 + hw) * 128 + (i & 1) * 32);
        tma_load_t(sbase + OFF_RA + (2 + hw) * SLOT, &tm_x0, fb, srcb(jj, 2 + hw) * 128, mm * 128);
        mbar_arrive_local(fb + 32);
        if (PRL == 0) PROFT(446 + hw);
      }
      __syncwarp();
      const unsigned epoch = hw ? __shfl_sync(0xffffffffu, epoch0, 31) : ld_relaxed(prm.epoch), ep1 = epoch + 1;
      const bool el = elect_one();
      cluster_wait();
      if (hw == 0) {
        mbar_wait_sl(bar_full + 8, 0);
        if (lane < 7) prefetch_tmap(lane == 0 ? &tm_os : lane == 1 ? &tm_o : lane == 2 ? &tm_wf : lane == 3 ? &tm_wqB : lane == 4 ? &tm_woA : lane == 5 ? &tm_woB : &tm_phi);
#pragma unroll 1
        for (int i = 0; i < (NLAYERS > 1 ? 5 : 0); i++) {
          if (i == 0) mbar_wait_sl(bar_done + FD0 * 8, 0);
          if (el) {
            if (i == 0) { mbar_expect_tx(bar_phi, 2 * SLOT + 8192); tma_load_2d(sbase + OFF_PHI, &tm_phi, bar_phi, 0, jj * 128); }
            else tma_load_2d(sbase + 12 * SLOT - 4096 + i * 4096, &tm_wqB, bar_phi, jj * 128 + ((i - 1) >> 1) * 64, mm * 64 + (~i & 1) * 32);
          }
          __syncwarp();
          __nanosleep(PFGAP);
        }
      } else {
        if (lane < 24) {
          const uint32_t one = (lane & 8) ? 0u : 0x3F80u << ((lane & 1) * 16), w = (lane >> 1) & 3;
          sts128(sbase + OFF_ID + lane * 16, w == 0 ? one : 0u, w == 1 ? one : 0u, w == 2 ? one : 0u, w == 3 ? one : 0u);
        }
#pragma unroll 1
        for (int b = 0; b < 2; b++) {
          float4* z = reinterpret_cast<float4*>(g_kv[b] + (jj * 4) * KVH + mm * (4 * KVH / 16)) + lane;
#pragma unroll
          for (int i = 0; i < 6; i++) z[i * 32] = make_float4(0.f, 0.f, 0.f, 0.f);
        }
#pragma unroll 1
        for (int i = 0; i < 16; i++) {
          const int b = i >> 2;
          const uint32_t v = (b == 0 ? O_BIT(0) : b == 1 ? X_BIT(0) : H_BIT(0)) + 1;
          uint4* p = b < 2 ? reinterpret_cast<uint4*>(g_obuf + (size_t)(b * S_LEN + mm * 128 + (i & 3) * 32 + (lane >> 3) * 8) * D_MODEL + jj * 128 + (b ? 0 : 64)) + (lane & 7)
                           : g_halo + (size_t)(mm * 8 + jj) * 512 + i * 32 + lane;
          *p = make_uint4(v, v, v, v);
        }
        fence_proxy_async_global();
      }
      __syncwarp();
      uint32_t chkp = 0;
#pragma unroll 1
      for (int lp = 0; lp < 8 * NLAYERS; lp++) {
        const int l = lp >> 3, tk = lp & 7, ph = tk ? 2 - hw : 0;
        const uint32_t par = l & 1;
        int lane; asm volatile("mov.u32 %0, %%laneid;" : "=r"(lane));
        if (tk == 5 || (hw && tk == 0 && l)) {
          const uint32_t bit = ph ? O_BIT(l) : X_BIT(l - 1);
          uint32_t slots = ph ? (uint32_t)(WO_ASLOT(par) >> (ph * 32 - 28)) : 0x8769876u;
          const uint32_t a0 = sbase + (lane & 7) * 126 + lane * 4 + (lane & 1) * 14;
#pragma unroll 1
          for (int c = 0; c < 7; c++, slots >>= 4) {
            const uint32_t cb = bar_chk + 112 - hw * 112 + c * 8;
#pragma unroll 1
            for (int it = 0; it < (1 << 12); it++) {
              mbar_wait_sl(cb, (chkp >> c) & 1);
              chkp ^= 1u << c;
              if (el) PROFL3(384 + ph * 8 + c);
              uint32_t bad;
              asm volatile("{\n.reg .b32 w<16>;\n"
                           "ld.shared.u32 w0, [%1 + 0];\n"
                           "ld.shared.u32 w1, [%1 + 1024];\n"
                           "ld.shared.u32 w2, [%1 + 2048];\n"
                           "ld.shared.u32 w3, [%1 + 3072];\n"
                           "ld.shared.u32 w4, [%1 + 4096];\n"
                           "ld.shared.u32 w5, [%1 + 5120];\n"
                           "ld.shared.u32 w6, [%1 + 6144];\n"
                           "ld.shared.u32 w7, [%1 + 7168];\n"
                           "ld.shared.u32 w8, [%1 + 8192];\n"
                           "ld.shared.u32 w9, [%1 + 9216];\n"
                           "ld.shared.u32 w10, [%1 + 10240];\n"
                           "ld.shared.u32 w11, [%1 + 11264];\n"
                           "ld.shared.u32 w12, [%1 + 12288];\n"
                           "ld.shared.u32 w13, [%1 + 13312];\n"
                           "ld.shared.u32 w14, [%1 + 14336];\n"
                           "ld.shared.u32 w15, [%1 + 15360];\n"
                           "lop3.b32 w0, w0, w1, %2, 0x7E;\n"
                           "lop3.b32 w2, w2, w3, %2, 0x7E;\n"
                           "lop3.b32 w4, w4, w5, %2, 0x7E;\n"
                           "lop3.b32 w6, w6, w7, %2, 0x7E;\n"
                           "lop3.b32 w8, w8, w9, %2, 0x7E;\n"
                           "lop3.b32 w10, w10, w11, %2, 0x7E;\n"
                           "lop3.b32 w12, w12, w13, %2, 0x7E;\n"
                           "lop3.b32 w14, w14, w15, %2, 0x7E;\n"
                           "lop3.b32 w0, w0, w2, w4, 0xFE;\nlop3.b32 w6, w6, w8, w10, 0xFE;\nlop3.b32 w0, w0, w12, w14, 0xFE;\nlop3.b32 %0, w0, w6, 1, 0xA8;\n}\n"
                           : "=r"(bad) : "r"(a0 + (slots & 15) * SLOT), "r"(bit) : "memory");
              if (__all_sync(0xffffffffu, bad == 0)) break;
              if (el) {
                fence_proxy_async_smem();
                mbar_expect_tx(cb, SLOT);
                tma_load_t(sbase + (slots & 15) * SLOT, &tm_o, cb, srcb(jj, c) * 128 + (ph >> 1) * 64, mm * 128 + (ph ? 0 : S_LEN));
                RETRY_COUNT();
              }
              __syncwarp();
            }
            if (el) { mbar_arrive_local(bar_full + (c + (ph ? 25 + ph * 8 : 4)) * 8); PROFL3(416 + ph * 8 + c); PROF2V(); }
            __syncwarp();
          }
        } else if (hw && (tk & 5) == 1) {
          {
            const int hp = tk >> 1;
            const uint4* src = reinterpret_cast<const uint4*>(g_colsum[par][jj * 64 + hp * 32 + lane]);
            uint32_t bad;
            int it = 0;
            float c[6];
            do {
              bad = 0;
#pragma unroll
              for (int p = 0; p < 3; p++) {
                const uint4 v = ld_ll(src + ((par && p < 2) ? (hp ? -32 : 512) + p * 32 : p * 512));
                bad |= (v.y ^ ep1) | (v.w ^ ep1);
                c[2 * p] = __uint_as_float(v.x) + __uint_as_float(v.z); c[2 * p + 1] = __uint_as_float(v.y) + __uint_as_float(v.w);
              }
              bad &= 3;
              if (bad) __nanosleep(CSGAP);
            } while (bad && ++it < (1 << 16));
#pragma unroll
            for (int p = 0; p < 6; p++) {
              uint32_t h, m, lo;
              split3(c[p], h, m, lo);
              sts128(sbase + OFF_LNB + hp * 4096 + (p >> 1) * 1024 + lane * 32 + (p & 1) * 16, h | (m << 16), h | (lo << 16), h | (m << 16), lo | (m << 16));
            }
            fence_proxy_async_smem();
            __syncwarp();
            if (el) { mbar_arrive_local(hp ? bar_stat2 : bar_stat); if (hp == 0) PROFT(324 + l * 16); }
            __syncwarp();
          }
        } else if (tk == 0) {
          mbar_wait_sl(bar_done + (l ? 24 : 56), par);
          const uint4* sp = reinterpret_cast<const uint4*>(g_stats + (size_t)(mm * 128) * 8) + lane;
          if (el) PROFL3(484);
#pragma unroll 1
          for (int hf = 2 * hw; hf < (l ? 4 : 2 + 2 * hw); hf++) {
            if (NLAYERS > 1 && l == 0 && el) tma_load_2d(sbase + 11 * SLOT + hf * 4096, &tm_wqB, bar_phi, 1024 + jj * 128 + (hf >> 1) * 64, mm * 64 + (hf & 1) * 32);
            __syncwarp();
            uint4 v[4];
            uint32_t bad;
            int it = 0;
            do {
              bad = 0;
#pragma unroll
              for (int i = 0; i < 4; i++) { v[i] = ld_ll(sp + (hf * 4 + i) * 32); bad |= (v[i].y ^ STAT_TAG(l)) | (v[i].w ^ STAT_TAG(l)); }
              bad &= 3;
              if (bad) __nanosleep(200);
            } while (bad && ++it < (1 << 16));
            __syncwarp();
            if (el) PROFL3(480 + hf);
            float mean = 0.f, m2 = 0.f;
#pragma unroll
            for (int i = 0; i < 4; i++) {
              float a = __uint_as_float(v[i].x) + __uint_as_float(v[i].z);
              a += __shfl_xor_sync(0xffffffffu, a, 1); a += __shfl_xor_sync(0xffffffffu, a, 2);
              a *= 0.125f;
              const float e0 = __uint_as_float(v[i].x) - a, e1 = __uint_as_float(v[i].z) - a;
              float q = fmaf(fmaf(e0, e0, e1 * e1), 128.f, __uint_as_float(v[i].y) + __uint_as_float(v[i].w));
              q += __shfl_xor_sync(0xffffffffu, q, 1); q += __shfl_xor_sync(0xffffffffu, q, 2);
              if ((lane & 3) == i) { mean = a; m2 = q; }
            }
            const uint32_t row = hf * 32 + (lane & 3) * 8 + (lane >> 2);
            uint32_t h, m, lo;
            split3(-0.5f * mean, h, m, lo);
            sts128(sbase + OFF_LNA + row * 16, h | (h << 16), m | (h << 16), lo | (m << 16), m | (lo << 16));
            sts32f(sbase + OFF_ST + row * 4, rsqrtf(m2 * (1.f / 1024.f) + 1e-5f));
          }
          if (hw) continue;
          fence_proxy_async_smem();
          __syncwarp();
          if (el) { mbar_arrive_local(bar_stat); PROFT(323 + l * 16); }
          __syncwarp();
#pragma unroll 1
          for (int i = 0; i < 8 - 4 * l; i++) {
            asm volatile("prefetch.global.L2 [%0];" :: "l"(i < 4 ? (l ? prm.wB_o : prm.wA_o) + (size_t)cta * 8192 + i * 2048 + lane * 64
                                                                 : prm.wB_qkv + (size_t)(cta * 8 + (i - 4) * 2 + (lane >> 4)) * 3072 + 2048 + (lane & 15) * 64));
            __nanosleep(PFGAP);
          }
        } else if (lp == 3) {
#pragma unroll 1
          for (int c = 0; c < (NLAYERS > 1 ? 8 : 0); c++) {
            if (!(c & 3)) { asm volatile("bar.sync %0, 288;" :: "r"(BAR_WF + (c >> 2)) : "memory"); fence_proxy_async_smem(); }
            if (el) {
              tma_store_2d(&tm_wf, sbase + 11 * SLOT + c * 4096, (c < 4 ? 1024 : -128) + jj * 128 + (c >> 1) * 64, mm * 64 + (c & 1) * 32);
              if (c == 7) {
                asm volatile("cp.async.bulk.commit_group;\ncp.async.bulk.wait_group.read 0;" ::: "memory");
                mbar_arrive_local(bar_phi + 8);
              } else __nanosleep(WFGAP);
            }
            __syncwarp();
          }
          if (el) { bulk_commit_wait(); signal_release(&g_flags.wfready[jj].v); PROFT(335); }
          __syncwarp();
        } else if (tk == 2 || tk == 4) {
          if (par) continue;
          const int i = tk >> 2;
          mbar_wait_sl(bar_done + (i ? HW1 : (hw ? 19 : HW0)) * 8, 0);
          const uint4* src = g_halo + (size_t)(mm * 8 + jj - 8) * 512 + i * 256 + hw * 128 + lane;
          uint4 v[4];
          int it = 0;
          bool ok;
          do {
#pragma unroll
            for (int j = 0; j < 4; j++) v[j] = mm ? ld_b128(src + j * 32) : make_uint4(H_BIT(l), 0, 0, 0);
            ok = __all_sync(0xffffffffu, (((v[0].x ^ H_BIT(l)) | (v[1].x ^ H_BIT(l)) | (v[2].x ^ H_BIT(l)) | (v[3].x ^ H_BIT(l))) & 1) == 0);
          } while (!ok && ++it < (1 << 16));
#pragma unroll
          for (int j = 0; j < 4; j++) sts128(sbase + OFF_S + hw * 8192 + j * 512 + lane * 16, v[j].x, v[j].y, v[j].z, v[j].w);
          __syncwarp();
          if (el) { mbar_arrive_local(bar_halo + hw * 8); PROFT(331 + l * 16 + i * 2 + hw); }
          __syncwarp();
        } else if (tk == 6 && hw == 0 && l < NLAYERS - 1) {
          bar_sync<BAR_X1, 288>();
          if (el) {
            PROFT(328 + l * 16);
            mbar_wait_sl(bar_full + XD * 8, par ^ 1);
            tma_store_t(&tm_o, sbase + 11 * SLOT, jj * 128 + 64, mm * 128 + S_LEN);
            bulk_commit_wait();
            signal_release(&g_flags.xready[l + 1][mm].v);
            PROFT(330 + l * 16);
          }
          __syncwarp();
        }
      }
    }
    cluster_sync();
  } else {
    asm volatile("setmaxnreg.inc.sync.aligned.u32 232;");
    const int wg = warp >> 2;
    const int r0 = warp * 16;
    const uint32_t pK = sbase + OFF_S, pV = sbase + OFF_S + SLOT;
#define PMASKS(on, bit) const uint32_t pm0 = ((on) && t == (g >> 1)), pbit = (bit)
#define PBIT(w) (((w) & ~pm0) | (pbit & pm0))
#define LANE_CONSTS() \
    int lane; asm volatile("mov.u32 %0, %%laneid;" : "=r"(lane)); \
    const int g = lane >> 2, t = lane & 3; \
    const uint32_t srowoff = (r0 + (lane & 15)) * 128, lsw = (lane & 7) << 4, lhi = (lane >> 4) << 4, lsw2 = (lane & 6) << 3; \
    (void)g; (void)t; (void)srowoff; (void)lsw; (void)lhi; (void)lsw2;
    uint32_t stgp = 0, peer;
    asm volatile("mapa.shared::cluster.u32 %0, %1, %2;" : "=r"(peer) : "r"(sbase), "r"(rank ^ 1));
    peer -= sbase;
    const uint32_t dA0 = (((sbase & 0x3FFFF) + wg * 8192) >> 4) | 0x10000u, dB0 = ((sbase & 0x3FFFF) >> 4) | 0x2000000u;
#define DESC(lo, hi) ((uint64_t)(uint32_t)(lo) | ((uint64_t)(hi) << 32))
#define STG_ARRIVE() { __syncwarp(); if (elect_one()) mbar_arrive_local(bar_stg); }
#define STG_WAIT() { mbar_wait(bar_stg, stgp); stgp ^= 1; }
#define PROFS() do {} while (0)
#define REL(addr) { if (elect_one()) { mbar_arrive_local(addr); asm volatile("mbarrier.arrive.shared::cluster.b64 _, [%0];" :: "r"((addr) + peer) : "memory"); } }
#define QSTEP(ACC, DA, SC) { \
      const uint32_t da = (DA), db = dB0 + (ub & 0x18) * (QST >> 7); \
      mbar_wait(ub, par); \
      wgmma_fence(); \
      wgmma4_n192<SC>(ACC, da, db); \
      wgmma_commit(); PROFS(); }
#define QREL() { wgmma_wait<1>(); REL(ub + 376); ub += 8; }
#define RA_CUR (dA0 + (OFF_RA >> 4) + (ub & 0x18) * (SLOT >> 7))
#define PUMP1() { QSTEP(S1, RA_CUR, 1); QREL(); }
#define PUMPN() { wgmma_fence(); wgmma4_n192<1>(S1, RA_CUR, dB0 + (ub & 0x18) * (QST >> 7)); wgmma_commit(); PROFS(); QREL(); }
#define PUMP0() { PUMP1(); SCHED_FENCE(); }
#define WSTEP() { \
      const uint32_t s4 = (ub - bar_full - 256) >> 1; \
      const uint32_t da = dA0 + (((uint32_t)(WO_ASLOT(par) >> s4) & 15) << 10), db = dB0 + (((uint32_t)(WO_BSLOT >> s4) & 15) << 10); \
      mbar_wait(ub, par); \
      wgmma_fence(); \
      wgmma4_n128<1>(S1, da, db); \
      wgmma_commit(); PROFS(); \
      wgmma_wait<1>(); \
      if (s4) REL(ub + 376); \
      ub += 8; }
#define PUMPS(n) { _Pragma("unroll 1") for (int i_ = 0; i_ < (n); i_++) PUMP1(); }
#define LNSTEP(ACC, hh) { wgmma_fence(); wgmma_n192<1, 0>(ACC, make_desc(sbase + OFF_LNA + wg * 1024, 0, 128) ^ (1ull << 62), make_desc(sbase + OFF_LNB + (hh) * 4096, 0, 128) ^ (1ull << 62)); }
#define WARP_STORE(tm, tile, col, row) { fence_proxy_async_smem(); __syncwarp(); WARP_STORE0(tm, tile, col, row); }
#define WARP_STORE0(tm, tile, col, row) { \
      if (elect_one()) { tma_store_2d(tm, (tile) + r0 * 128, col, (row) + r0); asm volatile("cp.async.bulk.commit_group;" ::: "memory"); } __syncwarp(); }
#define TILE_CONSTS(base, on, bit) \
      uint32_t ta[5]; \
      { PMASKS(on, bit); (void)pbit; ta[4] = pm0; } \
      _Pragma("unroll") for (int j = 0; j < 4; j++) ta[j] = (base) + srowoff + ((((uint32_t)j << 5) + lhi) ^ lsw); \
      PINU(ta, 5); SCHED_FENCE(); \
      const uint32_t pm0 = ta[4], pbit = (bit)
#define X_OUT(pc, W) { \
      _Pragma("unroll") for (int j = 0; j < 4; j++) \
        stsm_x4(ta[j] + (pc) * SLOT, \
                PBIT(pack_bf16((W)[j * 8 + 0], (W)[j * 8 + 1])), PBIT(pack_bf16((W)[j * 8 + 2], (W)[j * 8 + 3])), \
                (pack_bf16((W)[j * 8 + 4], (W)[j * 8 + 5])), (pack_bf16((W)[j * 8 + 6], (W)[j * 8 + 7]))); }
#define REST_P1(SKEW) { \
      mbar_wait(bar_stat2, par); \
      LNSTEP(S1, 1); \
      wgmma_commit(); \
      _Pragma("unroll 1") while (ub < bar_full + 256) { \
        const bool hold = ub == bar_full + 256 - 8 * (SKEW) && wg == 0; \
        if (hold) { wgmma_wait<0>(); REL(ub + 376); bar_sync<BAR_SKEW, 256>(); } \
        QSTEP(S1, RA_CUR, 1); \
        if (ub == bar_full + 248 && wg == 1) bar_arrive<BAR_SKEW, 256>(); \
        wgmma_wait<1>(); if (!hold) REL(ub + 376); ub += 8; \
      } \
      mbar_wait(bar_done + (31 - (SKEW)) * 8, par);        \
      wgmma_wait<0>(); \
      ACC_FENCE(S1, 96); \
      REL(bar_done + 31 * 8); \
      PROF(13); }
#define FOLD(tile, rd) { \
          LANE_CONSTS(); \
          float d[32]; \
          ACC_DEF(d, 32); \
          mbar_wait(bar_phi, 0); \
          wgmma_fence(); \
          _Pragma("unroll") for (int i = 0; i < 2; i++) { \
            const uint64_t da = make_desc((tile) + wg * 8192 + i * 64, 16, 1024); \
            const uint64_t db = make_desc(sbase + OFF_PHI + wg * 4096 + i * 2048, 16, 512) ^ (3ull << 62); \
            wgmma_n32<0>(d + i * 16, da, db); wgmma_n32<1>(d + i * 16, da + 2, db + 64); \
          } \
          wgmma_commit(); \
          PUMP0(); \
          ACC_FENCE(d, 32); \
          bar_wg(wg); \
          _Pragma("unroll") for (int i = 0; i < 4; i++) { \
            const float* x = d + (i & 1) * 8 + (i >> 1) * 2; \
            if (rd) sts128((tile) + wg * 8192 + ((warp & 3) * 16 + (i >> 1) * 8 + g) * 128 + (((2 * t + (i & 1)) ^ g) << 4), \
                           pack_bf16(x[0], x[1]), pack_bf16(x[4], x[5]), pack_bf16(x[16], x[17]), pack_bf16(x[20], x[21])); \
            else stsm_x4((tile) + srowoff + ((((uint32_t)i << 5) + lhi) ^ lsw), pack_bf16(d[i * 8], d[i * 8 + 1]), pack_bf16(d[i * 8 + 2], d[i * 8 + 3]), \
                         pack_bf16(d[i * 8 + 4], d[i * 8 + 5]), pack_bf16(d[i * 8 + 6], d[i * 8 + 7])); \
          } \
          }
#define XM_ISSUE() { mbar_wait(bar_xr, par); wgmma_fence(); \
      wgmma_copy(T_, dA0 + (OFF_RA >> 4), make_desc(sbase + OFF_ID, 128, 128) ^ (1ull << 62)); }
#define COPYN(d, s, n) _Pragma("unroll") for (int i_ = 0; i_ < (n); i_++) { uint32_t c_; asm volatile("mov.b32 %0, %1;" : "=r"(c_) : "f"((s)[i_])); (d)[i_] = __uint_as_float(c_); }
#define COPY64(d, s) COPYN(d, s, 64)
#define XM_DONE() { ACC_FENCE(T_, 64); COPY64(S1, T_); ACC_FENCE(S1, 64); \
      __syncwarp(); if (elect_one()) mbar_arrive_local(bar_lx); }
#define LOAD_X() { \
      uint32_t xr[32]; \
      wgmma_wait<0>(); mbar_wait(bar_xr, par); \
      _Pragma("unroll") for (int j_ = 0; j_ < 8; j_++) \
        ldsm_x4(sbase + OFF_RA + (j_ >> 2) * SLOT + srowoff + (((j_ & 3) * 32 + lhi) ^ lsw), xr[4 * j_], xr[4 * j_ + 1], xr[4 * j_ + 2], xr[4 * j_ + 3]); \
      _Pragma("unroll") for (int i_ = 0; i_ < 32; i_++) { S1[2 * i_] = bf_lo(xr[i_]); S1[2 * i_ + 1] = bf_hi(xr[i_]); } \
      ACC_FENCE(S1, 64); }

    float S0[96], S1[96];
    if (lane == 0) epoch0 = ld_relaxed(prm.epoch);
    __syncwarp();
    uint32_t ub = bar_full;
    {
      constexpr int l = 0;
      constexpr uint32_t par = 0;
      (void)l;
      ACC_DEF(S0, 96);
      QSTEP(S0, RA_CUR, 0);
      PROF(0);
      SCHED_FENCE();
      cluster_wait();
      ub += 8;
#pragma unroll 1
      for (int i = 1; i < 5; i++) {
        QSTEP(S0, dA0 + (OFF_RA >> 4) + i * (SLOT >> 4), 1);
        QREL();
      }
    }
    const unsigned epoch = __shfl_sync(0xffffffffu, epoch0, 0), ep1 = epoch + 1;
#pragma unroll 1
    for (int l = 0;; l++) {
      const uint32_t par = l & 1;
      PROF(1);
      {
        LANE_CONSTS();
        uint32_t ta[4];
#pragma unroll
        for (int j = 0; j < 4; j++) ta[j] = pK + srowoff + ((((uint32_t)j << 5) + lhi) ^ lsw);
        float p0, p1, a0 = 0.f, a1 = 0.f, q0 = 0.f, q1 = 0.f;
#define STATS(j0, j1) _Pragma("unroll") for (int j = (j0); j < (j1); j++) { \
          uint32_t x[4]; \
          ldsm_x4(ta[j & 3] + (j >> 2) * SLOT, x[0], x[1], x[2], x[3]); \
          if (j == 0) { p0 = __shfl_sync(0xffffffffu, bf_lo(x[0]), lane & 28); p1 = __shfl_sync(0xffffffffu, bf_lo(x[1]), lane & 28); } \
          _Pragma("unroll") for (int i = 0; i < 4; i += 2) { \
            const float d0 = bf_lo(x[i]) - p0, d1 = bf_hi(x[i]) - p0, d2 = bf_lo(x[i + 1]) - p1, d3 = bf_hi(x[i + 1]) - p1; \
            a0 += d0 + d1; a1 += d2 + d3; \
            q0 = fmaf(d1, d1, fmaf(d0, d0, q0)); q1 = fmaf(d3, d3, fmaf(d2, d2, q1)); } } \
          asm volatile("" : "+f"(a0), "+f"(a1), "+f"(q0), "+f"(q1), "+f"(p0), "+f"(p1)); SCHED_FENCE()
        if (SB0) { STATS(0, SB0); }
        bar_wg(wg);
        QSTEP(S0, dA0 + ((OFF_S + SLOT) >> 4), 1);
        QREL();
        SCHED_FENCE();
        STATS(SB0, SB1);
        ACC_DEF(S1, 96);
        QSTEP(S1, dA0 + (OFF_S >> 4), 0);
        QREL();
        SCHED_FENCE();
        STATS(SB1, SB2);
        QSTEP(S1, dA0 + ((OFF_S + SLOT) >> 4), 1);
        QREL();
        SCHED_FENCE();
        STATS(SB2, 8);
#pragma unroll
        for (int o = 1; o <= 2; o <<= 1) {
          a0 += __shfl_xor_sync(0xffffffffu, a0, o); a1 += __shfl_xor_sync(0xffffffffu, a1, o);
          q0 += __shfl_xor_sync(0xffffffffu, q0, o); q1 += __shfl_xor_sync(0xffffffffu, q1, o);
        }
        if (t == 1) { a0 = a1; q0 = q1; p0 = p1; }
        if (t < 2) st_b64(g_stats + (size_t)(mm * 128 + r0 + g + t * 8) * 8 + jj, __float_as_uint(fmaf(a0, 1.f / 128.f, p0)),
                          (__float_as_uint(fmaxf(fmaf(a0 * (-1.f / 128.f), a0, q0), 0.f)) & ~3u) | STAT_TAG(l));
        if (l) { asm volatile("cp.async.bulk.wait_group 0;" ::: "memory"); bar_arrive<BAR_X1, 288>(); }
#pragma unroll 1
        while (ub < bar_full + 144) {
          QSTEP(S0, RA_CUR, 1);
          if (ub == bar_full + 64) PROF(2);
          QREL();
        }
      }
      LANE_CONSTS();
      mbar_wait(bar_stat, par);
      LNSTEP(S0, 0);
      wgmma_commit();
      const float rs0 = lds32f(sbase + OFF_ST + (r0 + g) * 4), rs1 = lds32f(sbase + OFF_ST + (r0 + g + 8) * 4);
      PUMP0();
      ACC_FENCE(S0, 96);
      PROF(3);
      if (!par) {
        constexpr uint32_t par = 0;
        uint32_t qa[16];
        uint32_t kf[24], vf[24];
#define DRAIN_A(ACC, hp, PMP) { \
          LANE_CONSTS(); \
          FRAG(kf, ACC + 32, 0, (hp) * 2); \
          PMP; \
          FRAG(vf, ACC + 64, 1, (hp) * 2 + 1); \
          _Pragma("unroll") for (int i_ = 0; i_ < 16; i_++) qa[i_] = pack_bf16(ACC[2 * i_], ACC[2 * i_ + 1]); \
          PINU(qa, 16); }
        DRAIN_A(S0, 0, PUMP0());
        if (l == 0 && NLAYERS > 1) {
#pragma unroll 1
          for (int rd = 1; rd >= 0; rd--) {
            FOLD(sbase + (12 - rd) * SLOT, rd);
            asm volatile("bar.arrive %0, 288;" :: "r"(BAR_WF + 1 - rd) : "memory");
          }
        }
        PUMPS(FPUMP);
#pragma unroll 1
        for (int h = 0; h < 2; h++) {
          PROFH(4, 16);
          LANE_CONSTS();
          FRAG_PUT(kf + 16, 0); FRAG_PUT(vf + 16, 1);
          STG_ARRIVE();
          if (h) { PROF(8); LOAD_X(); PROF(9); WSTEP(); if (elect_one()) mbar_arrive_local(bar_lx);   PROF(10); } else PUMPS(HPUMP2);
          const bool gt0 = 2 * t > g, gt1 = 2 * t >= g;
          uint32_t msk[2] = {(gt0 ? 0xFFFFu : 0u) | (gt1 ? 0xFFFF0000u : 0u), g == 2 * t ? 0x10001u : 0u};
          PINU(msk, 2);
          TILE_CONSTS(sbase, false, 0);
          (void)pm0; (void)pbit;
          if (h) PROF(12);
          STG_WAIT();
          if (h) PROF(14);
          if (warp < 2) mbar_wait(bar_halo, h);
          if (h) PROF(15);
          if (h == 0) mbar_wait(ub, par);
          FRAG_GET(kf, 0);
          PROFH(5, 17);
          float s[2][3][4];
#pragma unroll
          for (int ks = 0; ks < 2; ks++)
#pragma unroll
            for (int i = 0; i < 6; i++) {
              const int hh = i & 1, jb = 2 - (i >> 1);
              const uint32_t* b = kf + jb * 8 + hh * 4 + ks * 2;
              if (ks) mma_bf16(s[hh][jb], qa[hh * 8 + 4], qa[hh * 8 + 5], qa[hh * 8 + 6], qa[hh * 8 + 7], b[0], b[1]);
              else mma_bf16_z(s[hh][jb], qa[hh * 8], qa[hh * 8 + 1], qa[hh * 8 + 2], qa[hh * 8 + 3], b[0], b[1]);
            }
          if (h == 0) PUMPN()
          PROFH(6, 18);
          float va[2][2], vb[2][2], mx[2][2];
#pragma unroll
          for (int hh = 0; hh < 2; hh++) {
            va[hh][0] = gt0 ? s[hh][0][0] : s[hh][1][0];
            vb[hh][0] = gt1 ? s[hh][0][1] : s[hh][1][1];
            va[hh][1] = gt0 ? s[hh][1][2] : s[hh][2][2];
            vb[hh][1] = gt1 ? s[hh][1][3] : s[hh][2][3];
          }
          if (warp < 2 && mm == 0) {
#pragma unroll
            for (int hh = 0; hh < 2; hh++) { if (gt0) va[hh][0] = -INFINITY; if (gt1) vb[hh][0] = -INFINITY; }
          }
#pragma unroll
          for (int i = 0; i < 4; i++) mx[i >> 1][i & 1] = fmaxf(va[i >> 1][i & 1], vb[i >> 1][i & 1]);
#pragma unroll
          for (int o = 1; o <= 2; o <<= 1)
#pragma unroll
            for (int i = 0; i < 4; i++) mx[i >> 1][i & 1] = fmaxf(mx[i >> 1][i & 1], __shfl_xor_sync(0xffffffffu, mx[i >> 1][i & 1], o));
          const float sc0 = rs0 * (0.17677669529663687f * LOG2E), sc1 = rs1 * (0.17677669529663687f * LOG2E);
#pragma unroll
          for (int i = 0; i < 4; i++) {
            const float sc = (i & 1) ? sc1 : sc0, m = mx[i >> 1][i & 1];
            va[i >> 1][i & 1] = ex2((va[i >> 1][i & 1] - m) * sc); vb[i >> 1][i & 1] = ex2((vb[i >> 1][i & 1] - m) * sc);
            mx[i >> 1][i & 1] = va[i >> 1][i & 1] + vb[i >> 1][i & 1];
          }
          if (h == 0) { PIN(&va[0][0], 4); PIN(&vb[0][0], 4); PIN(&mx[0][0], 4); PUMP1(); }
          if (h) PROF(20);
          if (warp < 2) mbar_wait(bar_halo + 8, h);
          if (h) PROF(21);
          if (h == 0) mbar_wait(ub, par);
          FRAG_GET(vf, 1);
#pragma unroll
          for (int o = 1; o <= 2; o <<= 1)
#pragma unroll
            for (int i = 0; i < 4; i++) mx[i >> 1][i & 1] += __shfl_xor_sync(0xffffffffu, mx[i >> 1][i & 1], o);
          float o[8][4];
          uint32_t pa[4][2];
#pragma unroll
          for (int i = 0; i < 4; i++) {
            const float iv = rcp_fast(mx[i >> 1][i & 1]);
            const uint32_t w = pack_bf16(va[i >> 1][i & 1] * iv, vb[i >> 1][i & 1] * iv);
            pa[i][0] = w & msk[0]; pa[i][1] = w & ~msk[0];
          }
          PROFH(7, 19);
#pragma unroll
          for (int i = 7; i >= 0; i--) {
            const uint32_t* a = vf + (i >> 2) * 8 + (i & 3) * 2;
            mma_bf16_z(o[i], a[0], a[1], a[8], a[9], pa[(i & 2) + (i >> 2)][0], pa[(i & 2) + (i >> 2)][1]);
          }
          if (h == 0) PUMPN() else mbar_wait(bar_done + 30 * 8, par);
          if (NLAYERS > 1 && l + h == 0) mbar_wait(bar_phi + 8, 0);
          if (h) PROF(22);
          {
            const uint32_t pm0 = msk[1], pbit = O_BIT(l) * 0x10001u;
#pragma unroll
            for (int i = 0; i < 4; i++)
              stsm_x4_t(ta[i] + (h ? 3 : 12) * SLOT, PBIT(pack_bf16(o[i][0], o[i][1])), PBIT(pack_bf16(o[i + 4][0], o[i + 4][1])),
                        pack_bf16(o[i][2], o[i][3]), pack_bf16(o[i + 4][2], o[i + 4][3]));
          }
          WARP_STORE(&tm_os, sbase + (h ? 3 : 12) * SLOT, jj * 128 + h * 64, mm * 128);
          PROFH(11, 23);
          if (h) break;
          REST_P1(ASKEW);
          asm volatile("cp.async.bulk.wait_group.read 0;" ::: "memory");
          DRAIN_A(S1, 1, {});
        }
      } else {
        constexpr uint32_t par = 1;
        float st[32];
        const float c0 = rs0 * LOG2E, c1 = rs1 * LOG2E;
        { V_ADDR(pV, 0); STAGE_V(S0 + 64); }
        if (warp < 2) sts128(sbase + OFF_ONES + warp * 512 + lane * 16, 0x3F803F80u, 0x3F803F80u, 0x3F803F80u, 0x3F803F80u);
        scale32(st, S0, c0, c1);
        PIN(st, 32);
#define PHI_PIECE(c) { \
          e_[2 * (c)] = ex2(st[2 * (c)]); e_[2 * (c) + 1] = ex2(st[2 * (c) + 1]); \
          _Pragma("unroll") for (int k_ = 4 * (c); k_ < 4 * (c) + 4; k_++) m_[(c) >> 1] = (k_ & 7) ? fmaf(st[k_], st[k_], m_[(c) >> 1]) : st[k_] * st[k_]; \
          asm volatile("" : "+f"(e_[2 * (c)]), "+f"(e_[2 * (c) + 1]), "+f"(m_[(c) >> 1])); SCHED_FENCE(); }
#define PHI_FIN() { \
          big = __any_sync(0xffffffffu, !(fmaxf(fmaxf(m_[0], m_[1]), fmaxf(m_[2], m_[3])) < BIGLIM)); \
          if (__builtin_expect(big, 0)) { COPYN(e_, st, 16); } \
          _Pragma("unroll") for (int k_ = 0; k_ < 16; k_++) st[k_] = e_[k_]; \
          PIN(st, 16); }
#define KV_MMA(vs, IL) { \
          const uint32_t dp = dA0 + 12 * 1024 - wg * 2560, dv = dA0 + (vs) * 1024 + ((OFF_ONES - (vs) * SLOT - 16) << 12) - wg * (512 << 16); \
          STG_WAIT(); \
          fence_proxy_async_smem(); \
          wgmma_fence(); \
          _Pragma("unroll") for (int ks = 0; ks < 8; ks++) { \
            const uint64_t a = DESC(dp + ks * 128, 0x40000040), b = DESC(dv + ks * (64 - (64 << 16)), 0x80000020); \
            if ((IL) && ks) wgmma_fence(); \
            if (ks == 0) wgmma_n40<0, 1>(kv, a, b); else wgmma_n40<1, 1>(kv, a, b); \
            if (ks == 7) wgmma_commit(); \
            if (IL) PHI_PIECE(ks); } }
#define KV_RED1(i) if (h) red_v4(g_kv[l >> 1] + (jj * 4) * KVH + warp * 768 + lane * 4 + (i) * 128, S0[32 + (i) * 3], S0[33 + (i) * 3], S0[34 + (i) * 3], 1.f)
#define KV_REDS(n) { _Pragma("unroll") for (int i_ = 0; i_ < 6; i_++) if (((RPACE >> (4 * i_)) & 15) == (n)) KV_RED1(i_); }
#define KV_SEND(kp) { \
          float sd[9]; \
          _Pragma("unroll") for (int i = 0; i < 8; i++) { (kp)[i] = kv[i]; sd[i] = kv[8 + i]; } \
          (kp)[8] = rank ? kv[18] : kv[16]; sd[8] = rank ? kv[16] : kv[18]; \
          const uint32_t ra = sbase + peer + (warp * 32 + lane) * 4, rb = bar_kx + peer; \
          if (elect_one()) mbar_expect_tx(bar_kx, 1152); \
          _Pragma("unroll") for (int i = 0; i < 2; i++) \
            asm volatile("st.async.weak.shared::cluster.mbarrier::complete_tx::bytes.v4.f32 [%0], {%1, %2, %3, %4}, [%5];" \
                         :: "r"(ra + (warp * 32 + lane) * 12 + OFF_PHI + i * 4096), "f"(sd[4 * i]), "f"(sd[4 * i + 1]), "f"(sd[4 * i + 2]), "f"(sd[4 * i + 3]), "r"(rb) : "memory"); \
          asm volatile("st.async.weak.shared::cluster.mbarrier::complete_tx::bytes.f32 [%0], %1, [%2];" :: "r"(ra + OFF_LNB), "f"(sd[8]), "r"(rb) : "memory"); }
#define KV_RECV(kp, hp) { \
          float r_[9]; \
          float* kvg = g_kv[l >> 1] + (jj * 4 + (hp) * 2) * KVH + warp * 768 + rank * 384 + lane * 4; \
          mbar_wait(bar_kx, l >> 1); \
          _Pragma("unroll") for (int i = 0; i < 2; i++) \
            asm volatile("ld.shared.v4.f32 {%0, %1, %2, %3}, [%4];" : "=f"(r_[4 * i]), "=f"(r_[4 * i + 1]), "=f"(r_[4 * i + 2]), "=f"(r_[4 * i + 3]) \
                         : "r"(sbase + OFF_PHI + i * 4096 + (warp * 32 + lane) * 16) : "memory"); \
          r_[8] = lds32f(sbase + OFF_LNB + (warp * 32 + lane) * 4); \
          _Pragma("unroll") for (int i = 0; i < 3; i++) red_v4(kvg + i * 128, (kp)[3 * i] + r_[3 * i], (kp)[3 * i + 1] + r_[3 * i + 1], (kp)[3 * i + 2] + r_[3 * i + 2], 2.f); }
#define KV_LOAD(hp) { \
          const uint4* kvg = reinterpret_cast<const uint4*>(g_kv[l >> 1] + (jj * 4 + (hp) * 2) * KVH) + warp * 192 + lane; \
          _Pragma("unroll") for (int i = 0; i < 6; i++) v[i] = ld_b128(kvg + i * 32); }
#define KVV(i) __uint_as_float((i) % 3 == 0 ? v[(i) / 3].x : ((i) % 3 == 1 ? v[(i) / 3].y : v[(i) / 3].z))
#define KV_TILE(hp) { \
          _Pragma("unroll 1") for (int it = 0; it < (1 << 16); it++) { \
            if (__all_sync(0xffffffffu, (v[0].w & v[1].w & v[2].w & v[3].w & v[4].w & v[5].w) == 0x41800000u)) break; \
            RETRY_COUNT(); \
            KV_LOAD(hp); \
          } \
          if (hp) PROF(26); else PROF(25); \
          const uint32_t e = lane & 7, jt = ((lane >> 1) & 4) + (e >> 1); \
          const uint32_t row = ((((warp >> 1) ^ wg) & 1) << 5) + ((jt & 1) << 4) + ((warp & 1) << 3) + (jt & 6) + (e & 1); \
          const uint32_t kd = pV + wg * 8192 + row * 128, ksw = (row & 7) << 4; \
          _Pragma("unroll") for (int i = 0; i < 2; i++) \
            stsm_x4(kd + ((i * 32 + lhi) ^ ksw), pack_bf16(KVV(i * 9), KVV(i * 9 + 1)), pack_bf16(KVV(i * 9 + 2), KVV(i * 9 + 3)), \
                    pack_bf16(KVV(i * 9 + 4), KVV(i * 9 + 5)), pack_bf16(KVV(i * 9 + 6), KVV(i * 9 + 7))); \
          stsm_x4(kd + ((64u + lhi) ^ ksw), pack_bf16(KVV(8), 1.f), pack_bf16(KVV(17), 1.f), 0u, 0u); }
#pragma unroll 1
        for (int h = 0; h < 2; h++) {
          PROFH(4, 6);
          PUMP0();
          LANE_CONSTS();
          const uint32_t dsw = (uint32_t)(g ^ (2 * t)) << 4, dst = ((t & 2) ? pK : sbase + 12 * SLOT) + (r0 + g) * 128;
          float e[16], f[16];
          KV_REDS(1);
          float sa = exps16_<0>(e, st);
          exps16_fix<0>(e, st, sa);
          asm volatile("" : "+f"(sa)); PIN(e, 16); PUMP0();
          if (h) STG_WAIT();
          KV_REDS(2);
          store16(e, sa, dst, dsw, 4);
          float sb = exps16_<1>(f, st);
          exps16_fix<1>(f, st, sb);
          asm volatile("" : "+f"(sb)); PIN(f, 16); PUMP0();
          KV_REDS(3);
          store16(f, sb, dst, dsw, 0);
          float sc = exps16_<0>(e, st + 2);
          exps16_fix<0>(e, st + 2, sc);
          asm volatile("" : "+f"(sc)); PIN(e, 16); PUMP0();
          KV_REDS(4);
          store16(e, sc, dst + 1024, dsw, 4);
          float sd = exps16_<1>(f, st + 2);
          exps16_fix<1>(f, st + 2, sd);
          asm volatile("" : "+f"(sd)); PIN(f, 16); PUMP0();
          store16(f, sd, dst + 1024, dsw, 0);
          PROFH(5, 7);
          if (h) break;
          {
            float kv[20];
            ACC_DEF(kv, 20);
            STG_ARRIVE();
            float e_[16], m_[4];
            KV_MMA(11, 0);
            PUMP0();
            ACC_FENCE(kv, 20);
            STG_ARRIVE();
            scale32(st, S0 + 32, c0, c1);
            PIN(st, 32);
            {
              COPYN(S0 + 32, kv, 8); COPYN(S0 + 40, kv + 16, 1); COPYN(S0 + 41, kv + 8, 8); COPYN(S0 + 49, kv + 18, 1);
              const int h = 1;
              KV_REDS(0);
            }
          }
        }
        bool big;
        uint4 v[6];
        {
          float kv[20];
          { LANE_CONSTS(); KV_LOAD(0); }
          mbar_wait(bar_stat2, par);
          ub = bar_full + 240;
          LNSTEP(S1, 1);
          PUMP1();
          if (wg == 0) bar_sync<BAR_SKEW, 256>();
          QSTEP(S1, RA_CUR, 1);
          if (wg == 1) bar_arrive<BAR_SKEW, 256>();
          QREL();
          { LANE_CONSTS(); KV_TILE(0); }
          LANE_CONSTS();
          V_ADDR(sbase + 3 * SLOT, rank * 32);
          PINU(va_, 2);
          mbar_wait(bar_done + 30 * 8, par);
          wgmma_wait<0>();
          ACC_FENCE(S1, 96);
          PROF(13);
          STAGE_V(S1 + 64);
          STG_ARRIVE();
          REL(bar_done + 31 * 8);
          scale32(st, S1, c0, c1);
          PIN(st, 32);
          PROF(16);
          ACC_DEF(kv, 20);
          float e_[16], m_[4];
          KV_MMA(3, 1);
          SCHED_FENCE();
          PROF(14);
          PHI_FIN();
          SCHED_FENCE();
          PROF(15);
          wgmma_wait<0>();
          ACC_FENCE(kv, 20);
          PROF(12);
          { float kp[9]; KV_SEND(kp); _Pragma("unroll") for (int i = 0; i < 3; i++) v[i] = make_uint4(__float_as_uint(kp[3 * i]), __float_as_uint(kp[3 * i + 1]), __float_as_uint(kp[3 * i + 2]), 0u); }
#define VDEF(i0) _Pragma("unroll") for (int i = (i0); i < 6; i++) asm volatile("" : "=r"(v[i].x), "=r"(v[i].y), "=r"(v[i].z), "=r"(v[i].w))
          VDEF(3);
          PROF(17);
        }
#pragma unroll 1
        for (int h = 0; h < 2; h++) {
          const uint32_t pO = sbase + (h ? 3 : 8) * SLOT;
          LANE_CONSTS();
          uint32_t fq[32];
          if (h) { KV_LOAD(1); phiq_a(st, big); PIN(st, 16); PROF(31); }
          PROFH(18, 32);
          SCHED_FENCE();
          phiq_b<1>(fq, st, big); PINU(fq, 16); PIN(st + 16, 16);
          SCHED_FENCE();
          PROFH(8, 9);
          if (h) {
            asm volatile("cp.async.bulk.wait_group.read 0;" ::: "memory");
            mbar_wait(bar_lx, par);
            PROF(30);
            KV_TILE(1);
            STG_ARRIVE();
          }
          SCHED_FENCE();
          if (h == 0) {
            float kp[9];
#pragma unroll
            for (int i = 0; i < 9; i++) kp[i] = KVV(i);
            KV_RECV(kp, 1);
            SCHED_FENCE();
          }
          phiq_b<0>(fq + 16, st + 16, big); PINU(fq + 16, 16);
          PROFH(10, 21);
          if (h) { STG_WAIT(); fence_proxy_async_smem(); }
          wgmma_wait<0>();
          ACC_FENCE(S1, 64);
          PROFH(19, 33);
          float o[4][20];
#define O_MMA(hh) { \
            const uint64_t db = make_desc(pV + (hh) * 8192, 16, 1024); \
            ACC_DEF(o[(hh) * 2], 20); ACC_DEF(o[(hh) * 2 + 1], 20); \
            wgmma_fence(); \
            wgmma_n40_rs<0>(o[(hh) * 2], fq + (hh) * 16, db + 256); wgmma_n40_rs<0>(o[(hh) * 2 + 1], fq + (hh) * 16 + 8, db); \
            wgmma_n40_rs<1>(o[(hh) * 2], fq + (hh) * 16 + 4, db + 384); wgmma_n40_rs<1>(o[(hh) * 2 + 1], fq + (hh) * 16 + 12, db + 128); \
            wgmma_commit(); }
          O_MMA(0);
          SCHED_FENCE();
          PMASKS(true, O_BIT(l));
#pragma unroll
          for (int hh = 0; hh < 2; hh++) {
            wgmma_wait<0>();
            ACC_FENCE(o[hh * 2], 20); ACC_FENCE(o[hh * 2 + 1], 20);
            if (!hh) { O_MMA(1); SCHED_FENCE(); }
            if (hh) PROFH(22, 24);
            const float* x = o[hh * 2];
            const float* y = o[hh * 2 + 1];
            const float sx0 = x[17] * 0x1p-40f, sy0 = y[17] * 0x1p-40f, sx1 = x[19] * 0x1p-40f, sy1 = y[19] * 0x1p-40f;
            const float i0 = rcp_fast(fmaf(fmaf(x[17], 1e-6f, x[16]), sy0, y[16] * sx0)), i1 = rcp_fast(fmaf(fmaf(x[19], 1e-6f, x[18]), sy1, y[18] * sx1));
            const float ax0 = sy0 * i0, ay0 = sx0 * i0, ax1 = sy1 * i1, ay1 = sx1 * i1;
#pragma unroll
            for (int dp = 0; dp < 2; dp++)
              stsm_x4(pO + srowoff + ((hh * 64 + dp * 32 + lhi) ^ lsw),
                      PBIT(pack_bf16(fmaf(x[dp * 8], ax0, y[dp * 8] * ay0), fmaf(x[dp * 8 + 1], ax0, y[dp * 8 + 1] * ay0))),
                      PBIT(pack_bf16(fmaf(x[dp * 8 + 2], ax1, y[dp * 8 + 2] * ay1), fmaf(x[dp * 8 + 3], ax1, y[dp * 8 + 3] * ay1))),
                      (pack_bf16(fmaf(x[dp * 8 + 4], ax0, y[dp * 8 + 4] * ay0), fmaf(x[dp * 8 + 5], ax0, y[dp * 8 + 5] * ay0))),
                      (pack_bf16(fmaf(x[dp * 8 + 6], ax1, y[dp * 8 + 6] * ay1), fmaf(x[dp * 8 + 7], ax1, y[dp * 8 + 7] * ay1))));
          }
          WARP_STORE(&tm_os, pO, jj * 128 + h * 64, mm * 128);
          PROFH(20, 34);
          if (h) break;
          float T_[64];
          scale32(st, S1 + 32, c0, c1);
          PIN(st, 32);
          ACC_DEF(T_, 64);
          XM_ISSUE(); wgmma_commit();
          SCHED_FENCE();
          big = any_big(st);
          SCHED_FENCE();
          PROF(27);
          wgmma_wait<0>(); XM_DONE();
          PROF(28);
          bar_wg(wg);
          WSTEP();
          SCHED_FENCE();
          VDEF(0);
          PROF(29);
        }
      }
      __syncwarp();
      if (elect_one()) mbar_arrive_local(bar_epi);
      bar_wg(wg);
#pragma unroll 1
      while (ub < bar_full + 384) {
        if (FSK && l == NLAYERS - 1 && wg == 0 && ub == bar_full + 384 - 8 * FSK) bar_sync<BAR_SKEW, 256>();
        if (FSK && l == NLAYERS - 1 && wg == 1 && ub == bar_full + 376) { mbar_wait(ub, par); bar_arrive<BAR_SKEW, 256>(); }
        WSTEP();
        if (ub == bar_full + 8 * 41) { asm volatile("cp.async.bulk.wait_group.read 0;" ::: "memory"); PROF(35); }
        if (ub == bar_full + 8 * 42) PROF(36);
      }
      {
        float Wb[32];
        LANE_CONSTS();
        TILE_CONSTS(pK, l < NLAYERS - 1, X_BIT(l));
        if (l < NLAYERS - 1) mbar_wait(bar_full, par ^ 1);
        wgmma_wait<0>();
        ACC_FENCE(S1, 64);
        COPYN(Wb, S1 + 32, 32);
        PROF(37);
        uint32_t xa[16];
#pragma unroll
        for (int i = 0; i < 16; i++) { const uint32_t w = pack_bf16(S1[2 * i], S1[2 * i + 1]); xa[i] = (i & 2) ? w : PBIT(w); }
        PINU(xa, 16);
#define XA_OUT() _Pragma("unroll") for (int j = 0; j < 4; j++) stsm_x4(ta[j], xa[4 * j], xa[4 * j + 1], xa[4 * j + 2], xa[4 * j + 3])
        if (l == NLAYERS - 1) {
          XA_OUT();
          const uint32_t src = pK + (r0 + (lane >> 3)) * 128 + (((lane ^ (lane >> 3)) & 7) << 4);
          uint4* dst = reinterpret_cast<uint4*>(prm.out + (size_t)(mm * 128 + (warp >> 1) * 32 + (warp & 1) + (lane >> 3) * 2) * D_MODEL + jj * 128) + (lane & 7);
#pragma unroll
          for (int pc = 0; pc < 2; pc++) {
            if (pc) { PMASKS(false, 0); X_OUT(1, Wb); }
            __syncwarp();
            uint4 y[4];
#pragma unroll
            for (int i = 0; i < 4; i++)
              asm volatile("ld.shared.v4.u32 {%0, %1, %2, %3}, [%4];" : "=r"(y[i].x), "=r"(y[i].y), "=r"(y[i].z), "=r"(y[i].w) : "r"((src + pc * SLOT + i * 512) ^ ((i & 1) << 6)) : "memory");
#pragma unroll
            for (int i = 0; i < 4; i++) dst[pc * 8 + i * 1024] = y[i];
            if (pc) PROF(39); else PROF(38);
          }
          break;
        }
        PROF(38);
        XA_OUT();
        ACC_DEF(S0, 96);
        wgmma_fence();
        wgmma_n192_rs<0>(S0, xa, dB0);
#pragma unroll
        for (int k = 1; k < RSK; k++) wgmma_n192_rs<1>(S0, xa + 4 * k, dB0 + 128 * k);
        wgmma_commit();
        WARP_STORE(&tm_os, pK, jj * 128, mm * 128 + S_LEN);
        if (RSK < 4) {
          wgmma_fence();
#pragma unroll
          for (int k = RSK; k < 4; k++) wgmma_n192_rs<1>(S0, xa + 4 * k, dB0 + 128 * k);
          wgmma_commit();
        }
        { const int ln_ = l + 1, l = ln_; const uint32_t ub = bar_full; (void)l; (void)ub; PROFS(); }
        REL(bar_done + 47 * 8);
        ub = bar_full + 8;
        PROF(39);
        { PMASKS(false, 0); X_OUT(1, Wb); }
        fence_proxy_async_smem();
      }
    }
    cluster_sync();
    if (threadIdx.x == 0) PROFT(487);
  }
}

typedef CUresult (*PFN_encode)(CUtensorMap*, CUtensorMapDataType, cuuint32_t, void*, const cuuint64_t*, const cuuint64_t*,
                               const cuuint32_t*, const cuuint32_t*, CUtensorMapInterleave, CUtensorMapSwizzle,
                               CUtensorMapL2promotion, CUtensorMapFloatOOBfill);

CUtensorMap make_map(PFN_encode enc, const void* ptr, uint64_t inner, uint64_t outer, uint32_t box_inner, uint32_t box_outer,
                     CUtensorMapSwizzle swz = CU_TENSOR_MAP_SWIZZLE_128B, int promo = CU_TENSOR_MAP_L2_PROMOTION_L2_256B) {
  CUtensorMap m;
  cuuint64_t dims[2] = {inner, outer};
  cuuint64_t strides[1] = {inner * 2};
  cuuint32_t box[2] = {box_inner, box_outer};
  cuuint32_t es[2] = {1, 1};
  enc(&m, CU_TENSOR_MAP_DATA_TYPE_BFLOAT16, 2, const_cast<void*>(ptr), dims, strides, box, es, CU_TENSOR_MAP_INTERLEAVE_NONE,
      swz, (CUtensorMapL2promotion)promo, CU_TENSOR_MAP_FLOAT_OOB_FILL_NONE);
  return m;
}

CUtensorMap make_tile_map(PFN_encode enc, const void* ptr, uint64_t rows, bool by_parity, int promo) {
  CUtensorMap m;
  cuuint64_t dims[4] = {D_MODEL, 16, 2, rows / 32};
  cuuint64_t strides[3] = {by_parity ? 4096u : 2048u, by_parity ? 2048u : 32768u, 65536};
  cuuint32_t box[4] = {64, 16, 2, 4};
  cuuint32_t es[4] = {1, 1, 1, 1};
  enc(&m, CU_TENSOR_MAP_DATA_TYPE_BFLOAT16, 4, const_cast<void*>(ptr), dims, strides, box, es, CU_TENSOR_MAP_INTERLEAVE_NONE,
      CU_TENSOR_MAP_SWIZZLE_128B, (CUtensorMapL2promotion)promo, CU_TENSOR_MAP_FLOAT_OOB_FILL_NONE);
  return m;
}

}

extern "C" void kernel_launch(void* const* d_in, const int* in_sizes, int n_in, void* d_out, int out_size) {
  (void)in_sizes; (void)n_in; (void)out_size;
  static PFN_encode enc = nullptr;
  if (!enc) {
    void* fn = nullptr;
    cudaDriverEntryPointQueryResult qr;
    cudaGetDriverEntryPoint("cuTensorMapEncodeTiled", &fn, cudaEnableDefault, &qr);
    enc = (PFN_encode)fn;
    cudaFuncSetAttribute(mega_kernel, cudaFuncAttributeMaxDynamicSharedMemorySize, SMEM_BYTES);
  }
  Params prm;
  prm.wA_o = (const __nv_bfloat16*)d_in[2];
  prm.wB_qkv = (const __nv_bfloat16*)d_in[4];
  prm.wB_o = (const __nv_bfloat16*)d_in[6];
  prm.out = (__nv_bfloat16*)d_out;
  void *obuf = nullptr, *wf = nullptr, *fl = nullptr;
  cudaGetSymbolAddress(&fl, g_flags);
  prm.epoch = &static_cast<Flags*>(fl)->epoch.v;
  cudaGetSymbolAddress(&obuf, g_obuf);
  cudaGetSymbolAddress(&wf, g_wfold);
  CUtensorMap tm_x0 = make_tile_map(enc, d_in[0], S_LEN, true, XPROMO);
  CUtensorMap tm_os = make_map(enc, obuf, D_MODEL, 2 * S_LEN, 64, 16);
  CUtensorMap tm_o = make_tile_map(enc, obuf, 2 * S_LEN, false, OPROMO);
  CUtensorMap tm_wf = make_map(enc, wf, 2048, D_MODEL, 64, 32);
  CUtensorMap tm_wqA = make_map(enc, d_in[1], 3 * D_MODEL, D_MODEL, 64, 32, CU_TENSOR_MAP_SWIZZLE_128B, WPROMO);
  CUtensorMap tm_wqB = make_map(enc, prm.wB_qkv, 3 * D_MODEL, D_MODEL, 64, 32);
  CUtensorMap tm_woA = make_map(enc, prm.wA_o, D_MODEL, D_MODEL, 64, 64);
  CUtensorMap tm_woB = make_map(enc, prm.wB_o, D_MODEL, D_MODEL, 64, 64);
  CUtensorMap tm_phi = make_map(enc, d_in[5], 32, 1024, 32, 128, CU_TENSOR_MAP_SWIZZLE_64B);
  mega_kernel<<<NMAIN + NAUX, 384, SMEM_BYTES>>>(prm, tm_x0, tm_os, tm_o, tm_wf, tm_wqA, tm_wqB, tm_woA, tm_woB, tm_phi);
}
```

```cpp
#include <cuda_runtime.h>
#include <cuda.h>
#include <cuda_bf16.h>
#include <stdint.h>

#define NLAYERS 4

#define HPUMP2 1
#define ASKEW 2
#define FPUMP 3
#define PFGAP 100
#define POLLGAP 120
#define HW1 30
#define XPACE 0x06050401000000ull
#define HW0 18
#define XD 4
#define WFGAP 10
#define EARLY 4
#define BIGLIM 3600.f
#define SUMLO 0x1p-100f
#define SUMHI 0x1p100f
#define XPROMO 2
#define OPROMO 2
#define WPROMO 3
#define SB0 2
#define SB1 4
#define SB2 6
#define PROWS 7
#define SPD0 0
#define SPD1 0
#define SPD2 300
#define FRB 0x3535353535ull
#define NOB 0xFFFFFF00u
#define NO1 ~0u
#define NOX ~0u
#define FD0 3
#define CSGAP 300
#define AUXORD 0x76543210
#define FSK 3
#define OWNW0 1
#define OWNW1 2
#define RPACE 0x221100
#define RSK 2
namespace {

constexpr int S_LEN = 2048, D_MODEL = 1024;
constexpr int NAUX = 4, NMAIN = 128;
constexpr int SLOT = 16384;
constexpr int QST = 24576;
constexpr int OFF_RA = 6 * SLOT, OFF_S = 10 * SLOT;
constexpr int OFF_HALO = 13 * SLOT, OFF_LNB = OFF_HALO  , OFF_ONES = OFF_HALO + 3072;
constexpr int OFF_ST = OFF_HALO + 7168  , OFF_ID = OFF_HALO + 7680, OFF_PHI = OFF_HALO + 8192;
constexpr int OFF_BAR = 14 * SLOT;
constexpr int OFF_LNA = OFF_BAR + 1024;
constexpr int SMEM_BYTES = OFF_LNA + 2048;
#define WO_ASLOT(par) ((par) ? 0x9876CAB39876CA98ull : 0xBC7698A3BC7698BCull)
constexpr unsigned long long WO_BSLOT = 0x5432105421054210ull;
__device__ __forceinline__ int srcb(int j, int i) { return (i + (i >= j)) & 7; }
__device__ __forceinline__ int kslice(int j, int i) { return i < 2 ? 2 * j + i : (i < 9 ? 2 * srcb(j, i - 2) : 2 * srcb(j, i - 9) + 1); }
__device__ __forceinline__ int wslice(int j, int s) { return 2 * ((s & 7) ? srcb(j, (s & 7) - 1) : j) + (s >> 3); }
constexpr int KVH = 6 * 128 * 4;

struct __align__(128) Flag { unsigned v; unsigned pad[31]; };
struct Flags {
  Flag xready[4][16];
  Flag wfready[8];
  Flag done;
  Flag epoch;
};

__device__ Flags g_flags;
__device__ __nv_bfloat16 g_obuf[2 * S_LEN * D_MODEL];
#define O_BIT(l) ((epoch * NLAYERS + (l) + 1) & 1u)
#define X_BIT(l) ((epoch * (NLAYERS - 1) + (l) + 1) & 1u)
__device__ __nv_bfloat16 g_wfold[D_MODEL * 2048];
__device__ uint4 g_halo[16 * 8 * 512];
__device__ __align__(128) float g_kv[2][32 * KVH];
__device__ __align__(128) uint2 g_colsum[2][1536][2];
__device__ __align__(128) uint2 g_stats[S_LEN * 8];
#define H_BIT(l) (NLAYERS > 2 ? (uint32_t)((l) == 0) : (ep1 & 1))
#define STAT_TAG(l) ((ep1 * NLAYERS + (l) + 1) & 3u)

#define RETRY_COUNT()
#define PRL 3
#define PROFL 1
#define PROFW 0
#define PROF2V() do {} while (0)
#define PROFT(i) do {} while (0)
#define PROF(i) do {} while (0)
#define PROFH(i, j) do {} while (0)
#define PROFL3(i) do {} while (0)

__device__ __forceinline__ uint32_t smem_u32(const void* p) { return (uint32_t)__cvta_generic_to_shared(p); }
__device__ __forceinline__ bool elect_one() {
  uint32_t p;
  asm volatile("{\n.reg .pred p;\nelect.sync _|p, 0xffffffff;\nselp.u32 %0, 1, 0, p;\n}\n" : "=r"(p));
  return p != 0;
}
__device__ __forceinline__ void mbar_init(uint32_t bar, uint32_t cnt) {
  asm volatile("mbarrier.init.shared::cta.b64 [%0], %1;" :: "r"(bar), "r"(cnt));
}
__device__ __forceinline__ void mbar_expect_tx(uint32_t bar, uint32_t bytes) {
  asm volatile("mbarrier.arrive.expect_tx.shared::cta.b64 _, [%0], %1;" :: "r"(bar), "r"(bytes) : "memory");
}
#define mbar_wait(bar, parity) \
  asm volatile("{\n.reg .pred p, q;\nW_%=:\nmbarrier.try_wait.parity.shared::cta.b64 p, [%1], %2;\nadd.s32 %0, %0, -1;\n" \
               "setp.gt.and.s32 q, %0, 0, !p;\n@q bra.uni W_%=;\n}\n" : "+r"(budget) : "r"((uint32_t)(bar)), "r"((uint32_t)(parity)) : "memory")
#define mbar_wait_sl(bar, parity) \
  asm volatile("{\n.reg .pred p, q;\nW_%=:\nmbarrier.try_wait.parity.shared::cta.b64 p, [%1], %2, 20000;\nadd.s32 %0, %0, -64;\n" \
               "setp.gt.and.s32 q, %0, 0, !p;\n@q bra.uni W_%=;\n}\n" : "+r"(budget) : "r"((uint32_t)(bar)), "r"((uint32_t)(parity)) : "memory")
__device__ __forceinline__ void mbar_arrive_local(uint32_t bar) {
  asm volatile("mbarrier.arrive.shared::cta.b64 _, [%0];" :: "r"(bar) : "memory");
}
__device__ __forceinline__ void tma_load_2d(uint32_t dst, const CUtensorMap* tm, uint32_t bar, int c0, int c1) {
  asm volatile("cp.async.bulk.tensor.2d.shared::cluster.global.mbarrier::complete_tx::bytes [%0], [%1, {%3, %4}], [%2];"
               :: "r"(dst), "l"(tm), "r"(bar), "r"(c0), "r"(c1) : "memory");
}
__device__ __forceinline__ void tma_load_2d_mc(uint32_t dst, const CUtensorMap* tm, uint32_t bar, int c0, int c1) {
  asm volatile("cp.async.bulk.tensor.2d.shared::cluster.global.mbarrier::complete_tx::bytes.multicast::cluster [%0], [%1, {%3, %4}], [%2], %5;"
               :: "r"(dst), "l"(tm), "r"(bar), "r"(c0), "r"(c1), "h"((uint16_t)3) : "memory");
}
__device__ __forceinline__ void tma_store_2d(const CUtensorMap* tm, uint32_t src, int c0, int c1) {
  asm volatile("cp.async.bulk.tensor.2d.global.shared::cta.bulk_group [%0, {%2, %3}], [%1];"
               :: "l"(tm), "r"(src), "r"(c0), "r"(c1) : "memory");
}
__device__ __forceinline__ void tma_load_t(uint32_t dst, const CUtensorMap* tm, uint32_t bar, int c0, int row) {
  asm volatile("cp.async.bulk.tensor.4d.shared::cluster.global.mbarrier::complete_tx::bytes [%0], [%1, {%3, %5, %5, %4}], [%2];"
               :: "r"(dst), "l"(tm), "r"(bar), "r"(c0), "r"(row >> 5), "r"(0) : "memory");
}
__device__ __forceinline__ void tma_store_t(const CUtensorMap* tm, uint32_t src, int c0, int row) {
  asm volatile("cp.async.bulk.tensor.4d.global.shared::cta.bulk_group [%0, {%2, %4, %4, %3}], [%1];"
               :: "l"(tm), "r"(src), "r"(c0), "r"(row >> 5), "r"(0) : "memory");
}
__device__ __forceinline__ void bulk_commit_wait() {
  asm volatile("cp.async.bulk.commit_group;\ncp.async.bulk.wait_group 0;" ::: "memory");
}
__device__ __forceinline__ void prefetch_tmap(const CUtensorMap* tm) {
  asm volatile("prefetch.tensormap [%0];" :: "l"(tm) : "memory");
}
__device__ __forceinline__ void fence_proxy_async_global() { asm volatile("fence.proxy.async.global;" ::: "memory"); }
__device__ __forceinline__ void fence_proxy_async_smem() { asm volatile("fence.proxy.async.shared::cta;" ::: "memory"); }
__device__ __forceinline__ unsigned ld_relaxed(const unsigned* p) {
  unsigned v;
  asm volatile("ld.relaxed.gpu.global.u32 %0, [%1];" : "=r"(v) : "l"(p) : "memory");
  return v;
}
__device__ __forceinline__ void fence_acquire() { asm volatile("fence.acquire.gpu;" ::: "memory"); }
__device__ __forceinline__ void wait_flag(const unsigned* p, unsigned target) {
  int it = 0;
  while ((int)(ld_relaxed(p) - target) < 0 && ++it < (1 << 20)) {}
  fence_acquire();
}
__device__ __forceinline__ void signal_release(unsigned* p) {
  asm volatile("red.release.gpu.global.add.u32 [%0], 1;" :: "l"(p) : "memory");
}
template <int ID, int N> __device__ __forceinline__ void bar_arrive() { asm volatile("bar.arrive %0, %1;" :: "n"(ID), "n"(N) : "memory"); }
template <int ID, int N> __device__ __forceinline__ void bar_sync() { asm volatile("bar.sync %0, %1;" :: "n"(ID), "n"(N) : "memory"); }
__device__ __forceinline__ void bar_wg(int wg) { asm volatile("bar.sync %0, 128;" :: "r"(2 + wg) : "memory"); }
__device__ __forceinline__ void cluster_sync() {
  asm volatile("barrier.cluster.arrive.relaxed.aligned;\nbarrier.cluster.wait.aligned;" ::: "memory");
}
__device__ __forceinline__ void cluster_wait() { asm volatile("barrier.cluster.wait.acquire.aligned;" ::: "memory"); }
enum { BAR_X1 = 7, BAR_WF = 8  , BAR_SKEW = 10 };

__device__ __forceinline__ void wgmma_fence() { asm volatile("wgmma.fence.sync.aligned;" ::: "memory"); }
__device__ __forceinline__ void wgmma_commit() { asm volatile("wgmma.commit_group.sync.aligned;" ::: "memory"); }
template <int N> __device__ __forceinline__ void wgmma_wait() { asm volatile("wgmma.wait_group.sync.aligned %0;" :: "n"(N) : "memory"); }

template <int scale_d, int tnsp_b = 1> __device__ __forceinline__ void wgmma_n192(float* d, uint64_t descA, uint64_t descB) {
  asm volatile("{\n.reg .pred p;\nsetp.ne.b32 p, %98, 0;\n"
               "wgmma.mma_async.sync.aligned.m64n192k16.f32.bf16.bf16 {%0,%1,%2,%3,%4,%5,%6,%7,%8,%9,%10,%11,%12,%13,%14,%15,%16,%17,%18,%19,%20,%21,%22,%23,%24,%25,%26,%27,%28,%29,%30,%31,%32,%33,%34,%35,%36,%37,%38,%39,%40,%41,%42,%43,%44,%45,%46,%47,%48,%49,%50,%51,%52,%53,%54,%55,%56,%57,%58,%59,%60,%61,%62,%63,%64,%65,%66,%67,%68,%69,%70,%71,%72,%73,%74,%75,%76,%77,%78,%79,%80,%81,%82,%83,%84,%85,%86,%87,%88,%89,%90,%91,%92,%93,%94,%95}, %96, %97, p, 1, 1, 0, %99;\n}\n"
               : "+f"(d[0]), "+f"(d[1]), "+f"(d[2]), "+f"(d[3]), "+f"(d[4]), "+f"(d[5]), "+f"(d[6]), "+f"(d[7]), "+f"(d[8]), "+f"(d[9]), "+f"(d[10]), "+f"(d[11]), "+f"(d[12]), "+f"(d[13]), "+f"(d[14]), "+f"(d[15]), "+f"(d[16]), "+f"(d[17]), "+f"(d[18]), "+f"(d[19]), "+f"(d[20]), "+f"(d[21]), "+f"(d[22]), "+f"(d[23]), "+f"(d[24]), "+f"(d[25]), "+f"(d[26]), "+f"(d[27]), "+f"(d[28]), "+f"(d[29]), "+f"(d[30]), "+f"(d[31]), "+f"(d[32]), "+f"(d[33]), "+f"(d[34]), "+f"(d[35]), "+f"(d[36]), "+f"(d[37]), "+f"(d[38]), "+f"(d[39]), "+f"(d[40]), "+f"(d[41]), "+f"(d[42]), "+f"(d[43]), "+f"(d[44]), "+f"(d[45]), "+f"(d[46]), "+f"(d[47]), "+f"(d[48]), "+f"(d[49]), "+f"(d[50]), "+f"(d[51]), "+f"(d[52]), "+f"(d[53]), "+f"(d[54]), "+f"(d[55]), "+f"(d[56]), "+f"(d[57]), "+f"(d[58]), "+f"(d[59]), "+f"(d[60]), "+f"(d[61]), "+f"(d[62]), "+f"(d[63]), "+f"(d[64]), "+f"(d[65]), "+f"(d[66]), "+f"(d[67]), "+f"(d[68]), "+f"(d[69]), "+f"(d[70]), "+f"(d[71]), "+f"(d[72]), "+f"(d[73]), "+f"(d[74]), "+f"(d[75]), "+f"(d[76]), "+f"(d[77]), "+f"(d[78]), "+f"(d[79]), "+f"(d[80]), "+f"(d[81]), "+f"(d[82]), "+f"(d[83]), "+f"(d[84]), "+f"(d[85]), "+f"(d[86]), "+f"(d[87]), "+f"(d[88]), "+f"(d[89]), "+f"(d[90]), "+f"(d[91]), "+f"(d[92]), "+f"(d[93]), "+f"(d[94]), "+f"(d[95])
               : "l"(descA), "l"(descB), "n"(scale_d), "n"(tnsp_b));
}
template <int scale_d> __device__ __forceinline__ void wgmma4_n192(float* d, uint32_t da, uint32_t db) {
#define R_ "{%0,%1,%2,%3,%4,%5,%6,%7,%8,%9,%10,%11,%12,%13,%14,%15,%16,%17,%18,%19,%20,%21,%22,%23,%24,%25,%26,%27,%28,%29,%30,%31,%32,%33,%34,%35,%36,%37,%38,%39,%40,%41,%42,%43,%44,%45,%46,%47,%48,%49,%50,%51,%52,%53,%54,%55,%56,%57,%58,%59,%60,%61,%62,%63,%64,%65,%66,%67,%68,%69,%70,%71,%72,%73,%74,%75,%76,%77,%78,%79,%80,%81,%82,%83,%84,%85,%86,%87,%88,%89,%90,%91,%92,%93,%94,%95}"
  asm volatile("{\n.reg .pred p, q;\n.reg .b64 a, b;\nsetp.ne.b32 p, %98, 0;\nsetp.eq.b32 q, 0, 0;\nmov.b64 a, {%96, 0x40000040};\nmov.b64 b, {%97, 0x40000040};\n"
               "wgmma.mma_async.sync.aligned.m64n192k16.f32.bf16.bf16 " R_ ", a, b, p, 1, 1, 0, 1;\nadd.s64 a, a, 2;\nadd.s64 b, b, 128;\n"
               "wgmma.mma_async.sync.aligned.m64n192k16.f32.bf16.bf16 " R_ ", a, b, q, 1, 1, 0, 1;\nadd.s64 a, a, 2;\nadd.s64 b, b, 128;\n"
               "wgmma.mma_async.sync.aligned.m64n192k16.f32.bf16.bf16 " R_ ", a, b, q, 1, 1, 0, 1;\nadd.s64 a, a, 2;\nadd.s64 b, b, 128;\n"
               "wgmma.mma_async.sync.aligned.m64n192k16.f32.bf16.bf16 " R_ ", a, b, q, 1, 1, 0, 1;\n}\n"
               : "+f"(d[0]), "+f"(d[1]), "+f"(d[2]), "+f"(d[3]), "+f"(d[4]), "+f"(d[5]), "+f"(d[6]), "+f"(d[7]), "+f"(d[8]), "+f"(d[9]), "+f"(d[10]), "+f"(d[11]), "+f"(d[12]), "+f"(d[13]), "+f"(d[14]), "+f"(d[15]), "+f"(d[16]), "+f"(d[17]), "+f"(d[18]), "+f"(d[19]), "+f"(d[20]), "+f"(d[21]), "+f"(d[22]), "+f"(d[23]), "+f"(d[24]), "+f"(d[25]), "+f"(d[26]), "+f"(d[27]), "+f"(d[28]), "+f"(d[29]), "+f"(d[30]), "+f"(d[31]), "+f"(d[32]), "+f"(d[33]), "+f"(d[34]), "+f"(d[35]), "+f"(d[36]), "+f"(d[37]), "+f"(d[38]), "+f"(d[39]), "+f"(d[40]), "+f"(d[41]), "+f"(d[42]), "+f"(d[43]), "+f"(d[44]), "+f"(d[45]), "+f"(d[46]), "+f"(d[47]), "+f"(d[48]), "+f"(d[49]), "+f"(d[50]), "+f"(d[51]), "+f"(d[52]), "+f"(d[53]), "+f"(d[54]), "+f"(d[55]), "+f"(d[56]), "+f"(d[57]), "+f"(d[58]), "+f"(d[59]), "+f"(d[60]), "+f"(d[61]), "+f"(d[62]), "+f"(d[63]), "+f"(d[64]), "+f"(d[65]), "+f"(d[66]), "+f"(d[67]), "+f"(d[68]), "+f"(d[69]), "+f"(d[70]), "+f"(d[71]), "+f"(d[72]), "+f"(d[73]), "+f"(d[74]), "+f"(d[75]), "+f"(d[76]), "+f"(d[77]), "+f"(d[78]), "+f"(d[79]), "+f"(d[80]), "+f"(d[81]), "+f"(d[82]), "+f"(d[83]), "+f"(d[84]), "+f"(d[85]), "+f"(d[86]), "+f"(d[87]), "+f"(d[88]), "+f"(d[89]), "+f"(d[90]), "+f"(d[91]), "+f"(d[92]), "+f"(d[93]), "+f"(d[94]), "+f"(d[95])
               : "r"(da), "r"(db), "n"(scale_d));
#undef R_
}
template <int scale_d> __device__ __forceinline__ void wgmma4_n128(float* d, uint32_t da, uint32_t db) {
#define R_ "{%0,%1,%2,%3,%4,%5,%6,%7,%8,%9,%10,%11,%12,%13,%14,%15,%16,%17,%18,%19,%20,%21,%22,%23,%24,%25,%26,%27,%28,%29,%30,%31,%32,%33,%34,%35,%36,%37,%38,%39,%40,%41,%42,%43,%44,%45,%46,%47,%48,%49,%50,%51,%52,%53,%54,%55,%56,%57,%58,%59,%60,%61,%62,%63}"
  asm volatile("{\n.reg .pred p, q;\n.reg .b64 a, b;\nsetp.ne.b32 p, %66, 0;\nsetp.eq.b32 q, 0, 0;\nmov.b64 a, {%64, 0x40000040};\nmov.b64 b, {%65, 0x40000040};\n"
               "wgmma.mma_async.sync.aligned.m64n128k16.f32.bf16.bf16 " R_ ", a, b, p, 1, 1, 0, 1;\nadd.s64 a, a, 2;\nadd.s64 b, b, 128;\n"
               "wgmma.mma_async.sync.aligned.m64n128k16.f32.bf16.bf16 " R_ ", a, b, q, 1, 1, 0, 1;\nadd.s64 a, a, 2;\nadd.s64 b, b, 128;\n"
               "wgmma.mma_async.sync.aligned.m64n128k16.f32.bf16.bf16 " R_ ", a, b, q, 1, 1, 0, 1;\nadd.s64 a, a, 2;\nadd.s64 b, b, 128;\n"
               "wgmma.mma_async.sync.aligned.m64n128k16.f32.bf16.bf16 " R_ ", a, b, q, 1, 1, 0, 1;\n}\n"
               : "+f"(d[0]), "+f"(d[1]), "+f"(d[2]), "+f"(d[3]), "+f"(d[4]), "+f"(d[5]), "+f"(d[6]), "+f"(d[7]), "+f"(d[8]), "+f"(d[9]), "+f"(d[10]), "+f"(d[11]), "+f"(d[12]), "+f"(d[13]), "+f"(d[14]), "+f"(d[15]), "+f"(d[16]), "+f"(d[17]), "+f"(d[18]), "+f"(d[19]), "+f"(d[20]), "+f"(d[21]), "+f"(d[22]), "+f"(d[23]), "+f"(d[24]), "+f"(d[25]), "+f"(d[26]), "+f"(d[27]), "+f"(d[28]), "+f"(d[29]), "+f"(d[30]), "+f"(d[31]), "+f"(d[32]), "+f"(d[33]), "+f"(d[34]), "+f"(d[35]), "+f"(d[36]), "+f"(d[37]), "+f"(d[38]), "+f"(d[39]), "+f"(d[40]), "+f"(d[41]), "+f"(d[42]), "+f"(d[43]), "+f"(d[44]), "+f"(d[45]), "+f"(d[46]), "+f"(d[47]), "+f"(d[48]), "+f"(d[49]), "+f"(d[50]), "+f"(d[51]), "+f"(d[52]), "+f"(d[53]), "+f"(d[54]), "+f"(d[55]), "+f"(d[56]), "+f"(d[57]), "+f"(d[58]), "+f"(d[59]), "+f"(d[60]), "+f"(d[61]), "+f"(d[62]), "+f"(d[63])
               : "r"(da), "r"(db), "n"(scale_d));
#undef R_
}
template <int scale_d> __device__ __forceinline__ void wgmma_n32(float* d, uint64_t descA, uint64_t descB) {
  asm volatile("{\n.reg .pred p;\nsetp.ne.b32 p, %18, 0;\n"
               "wgmma.mma_async.sync.aligned.m64n32k16.f32.bf16.bf16 {%0,%1,%2,%3,%4,%5,%6,%7,%8,%9,%10,%11,%12,%13,%14,%15}, %16, %17, p, 1, 1, 0, 1;\n}\n"
               : "+f"(d[0]), "+f"(d[1]), "+f"(d[2]), "+f"(d[3]), "+f"(d[4]), "+f"(d[5]), "+f"(d[6]), "+f"(d[7]), "+f"(d[8]), "+f"(d[9]), "+f"(d[10]), "+f"(d[11]), "+f"(d[12]), "+f"(d[13]), "+f"(d[14]), "+f"(d[15])
               : "l"(descA), "l"(descB), "n"(scale_d));
}
template <int scale_d, int tnsp_a> __device__ __forceinline__ void wgmma_n40(float* d, uint64_t descA, uint64_t descB) {
  asm volatile("{\n.reg .pred p;\nsetp.ne.b32 p, %22, 0;\n"
               "wgmma.mma_async.sync.aligned.m64n40k16.f32.bf16.bf16 {%0,%1,%2,%3,%4,%5,%6,%7,%8,%9,%10,%11,%12,%13,%14,%15,%16,%17,%18,%19}, %20, %21, p, 1, 1, %23, 1;\n}\n"
               : "+f"(d[0]), "+f"(d[1]), "+f"(d[2]), "+f"(d[3]), "+f"(d[4]), "+f"(d[5]), "+f"(d[6]), "+f"(d[7]), "+f"(d[8]), "+f"(d[9]), "+f"(d[10]), "+f"(d[11]), "+f"(d[12]), "+f"(d[13]), "+f"(d[14]), "+f"(d[15]), "+f"(d[16]), "+f"(d[17]), "+f"(d[18]), "+f"(d[19])
               : "l"(descA), "l"(descB), "n"(scale_d), "n"(tnsp_a));
}
template <int scale_d> __device__ __forceinline__ void wgmma_n40_rs(float* d, const uint32_t* a, uint64_t descB) {
  asm volatile("{\n.reg .pred p;\nsetp.ne.b32 p, %25, 0;\n"
               "wgmma.mma_async.sync.aligned.m64n40k16.f32.bf16.bf16 {%0,%1,%2,%3,%4,%5,%6,%7,%8,%9,%10,%11,%12,%13,%14,%15,%16,%17,%18,%19}, {%20,%21,%22,%23}, %24, p, 1, 1, 1;\n}\n"
               : "+f"(d[0]), "+f"(d[1]), "+f"(d[2]), "+f"(d[3]), "+f"(d[4]), "+f"(d[5]), "+f"(d[6]), "+f"(d[7]), "+f"(d[8]), "+f"(d[9]), "+f"(d[10]), "+f"(d[11]), "+f"(d[12]), "+f"(d[13]), "+f"(d[14]), "+f"(d[15]), "+f"(d[16]), "+f"(d[17]), "+f"(d[18]), "+f"(d[19])
               : "r"(a[0]), "r"(a[1]), "r"(a[2]), "r"(a[3]), "l"(descB), "n"(scale_d));
}
__device__ __forceinline__ void wgmma_copy(float* d, uint32_t da, uint64_t descB) {
  asm volatile("{\n.reg .pred p;\n.reg .b64 a;\nsetp.ne.b32 p, 0, 0;\nmov.b64 a, {%64, 0x40000040};\n"
               "wgmma.mma_async.sync.aligned.m64n16k16.f32.bf16.bf16 {%0,%1,%2,%3,%4,%5,%6,%7}, a, %65, p, 1, 1, 0, 0;\nadd.s64 a, a, 2;\n"
               "wgmma.mma_async.sync.aligned.m64n16k16.f32.bf16.bf16 {%8,%9,%10,%11,%12,%13,%14,%15}, a, %65, p, 1, 1, 0, 0;\nadd.s64 a, a, 2;\n"
               "wgmma.mma_async.sync.aligned.m64n16k16.f32.bf16.bf16 {%16,%17,%18,%19,%20,%21,%22,%23}, a, %65, p, 1, 1, 0, 0;\nadd.s64 a, a, 2;\n"
               "wgmma.mma_async.sync.aligned.m64n16k16.f32.bf16.bf16 {%24,%25,%26,%27,%28,%29,%30,%31}, a, %65, p, 1, 1, 0, 0;\nadd.s64 a, a, 1018;\n"
               "wgmma.mma_async.sync.aligned.m64n16k16.f32.bf16.bf16 {%32,%33,%34,%35,%36,%37,%38,%39}, a, %65, p, 1, 1, 0, 0;\nadd.s64 a, a, 2;\n"
               "wgmma.mma_async.sync.aligned.m64n16k16.f32.bf16.bf16 {%40,%41,%42,%43,%44,%45,%46,%47}, a, %65, p, 1, 1, 0, 0;\nadd.s64 a, a, 2;\n"
               "wgmma.mma_async.sync.aligned.m64n16k16.f32.bf16.bf16 {%48,%49,%50,%51,%52,%53,%54,%55}, a, %65, p, 1, 1, 0, 0;\nadd.s64 a, a, 2;\n"
               "wgmma.mma_async.sync.aligned.m64n16k16.f32.bf16.bf16 {%56,%57,%58,%59,%60,%61,%62,%63}, a, %65, p, 1, 1, 0, 0;\n"
               "}\n"
               : "+f"(d[0]), "+f"(d[1]), "+f"(d[2]), "+f"(d[3]), "+f"(d[4]), "+f"(d[5]), "+f"(d[6]), "+f"(d[7]), "+f"(d[8]), "+f"(d[9]), "+f"(d[10]), "+f"(d[11]), "+f"(d[12]), "+f"(d[13]), "+f"(d[14]), "+f"(d[15]), "+f"(d[16]), "+f"(d[17]), "+f"(d[18]), "+f"(d[19]), "+f"(d[20]), "+f"(d[21]), "+f"(d[22]), "+f"(d[23]), "+f"(d[24]), "+f"(d[25]), "+f"(d[26]), "+f"(d[27]), "+f"(d[28]), "+f"(d[29]), "+f"(d[30]), "+f"(d[31]), "+f"(d[32]), "+f"(d[33]), "+f"(d[34]), "+f"(d[35]), "+f"(d[36]), "+f"(d[37]), "+f"(d[38]), "+f"(d[39]), "+f"(d[40]), "+f"(d[41]), "+f"(d[42]), "+f"(d[43]), "+f"(d[44]), "+f"(d[45]), "+f"(d[46]), "+f"(d[47]), "+f"(d[48]), "+f"(d[49]), "+f"(d[50]), "+f"(d[51]), "+f"(d[52]), "+f"(d[53]), "+f"(d[54]), "+f"(d[55]), "+f"(d[56]), "+f"(d[57]), "+f"(d[58]), "+f"(d[59]), "+f"(d[60]), "+f"(d[61]), "+f"(d[62]), "+f"(d[63])
               : "r"(da), "l"(descB));
}
template <int scale_d> __device__ __forceinline__ void wgmma_n192_rs(float* d, const uint32_t* a, uint32_t db) {
  asm volatile("{\n.reg .pred p;\n.reg .b64 b;\nsetp.ne.b32 p, %101, 0;\nmov.b64 b, {%100, 0x40000040};\n"
               "wgmma.mma_async.sync.aligned.m64n192k16.f32.bf16.bf16 {%0,%1,%2,%3,%4,%5,%6,%7,%8,%9,%10,%11,%12,%13,%14,%15,%16,%17,%18,%19,%20,%21,%22,%23,%24,%25,%26,%27,%28,%29,%30,%31,%32,%33,%34,%35,%36,%37,%38,%39,%40,%41,%42,%43,%44,%45,%46,%47,%48,%49,%50,%51,%52,%53,%54,%55,%56,%57,%58,%59,%60,%61,%62,%63,%64,%65,%66,%67,%68,%69,%70,%71,%72,%73,%74,%75,%76,%77,%78,%79,%80,%81,%82,%83,%84,%85,%86,%87,%88,%89,%90,%91,%92,%93,%94,%95}, {%96,%97,%98,%99}, b, p, 1, 1, 1;\n}\n"
               : "+f"(d[0]), "+f"(d[1]), "+f"(d[2]), "+f"(d[3]), "+f"(d[4]), "+f"(d[5]), "+f"(d[6]), "+f"(d[7]), "+f"(d[8]), "+f"(d[9]), "+f"(d[10]), "+f"(d[11]), "+f"(d[12]), "+f"(d[13]), "+f"(d[14]), "+f"(d[15]), "+f"(d[16]), "+f"(d[17]), "+f"(d[18]), "+f"(d[19]), "+f"(d[20]), "+f"(d[21]), "+f"(d[22]), "+f"(d[23]), "+f"(d[24]), "+f"(d[25]), "+f"(d[26]), "+f"(d[27]), "+f"(d[28]), "+f"(d[29]), "+f"(d[30]), "+f"(d[31]), "+f"(d[32]), "+f"(d[33]), "+f"(d[34]), "+f"(d[35]), "+f"(d[36]), "+f"(d[37]), "+f"(d[38]), "+f"(d[39]), "+f"(d[40]), "+f"(d[41]), "+f"(d[42]), "+f"(d[43]), "+f"(d[44]), "+f"(d[45]), "+f"(d[46]), "+f"(d[47]), "+f"(d[48]), "+f"(d[49]), "+f"(d[50]), "+f"(d[51]), "+f"(d[52]), "+f"(d[53]), "+f"(d[54]), "+f"(d[55]), "+f"(d[56]), "+f"(d[57]), "+f"(d[58]), "+f"(d[59]), "+f"(d[60]), "+f"(d[61]), "+f"(d[62]), "+f"(d[63]), "+f"(d[64]), "+f"(d[65]), "+f"(d[66]), "+f"(d[67]), "+f"(d[68]), "+f"(d[69]), "+f"(d[70]), "+f"(d[71]), "+f"(d[72]), "+f"(d[73]), "+f"(d[74]), "+f"(d[75]), "+f"(d[76]), "+f"(d[77]), "+f"(d[78]), "+f"(d[79]), "+f"(d[80]), "+f"(d[81]), "+f"(d[82]), "+f"(d[83]), "+f"(d[84]), "+f"(d[85]), "+f"(d[86]), "+f"(d[87]), "+f"(d[88]), "+f"(d[89]), "+f"(d[90]), "+f"(d[91]), "+f"(d[92]), "+f"(d[93]), "+f"(d[94]), "+f"(d[95])
               : "r"(a[0]), "r"(a[1]), "r"(a[2]), "r"(a[3]), "r"(db), "n"(scale_d));
}
__device__ __forceinline__ uint64_t make_desc(uint32_t addr, uint32_t lbo_bytes, uint32_t sbo_bytes) {
  return (uint64_t)((addr & 0x3FFFF) >> 4) | ((uint64_t)(lbo_bytes >> 4) << 16) | ((uint64_t)(sbo_bytes >> 4) << 32) | (1ull << 62);
}

__device__ __forceinline__ void ldsm_x4(uint32_t addr, uint32_t& r0, uint32_t& r1, uint32_t& r2, uint32_t& r3) {
  asm volatile("ldmatrix.sync.aligned.m8n8.x4.shared.b16 {%0,%1,%2,%3}, [%4];" : "=r"(r0), "=r"(r1), "=r"(r2), "=r"(r3) : "r"(addr) : "memory");
}
__device__ __forceinline__ void ldsm_x4_t(uint32_t addr, uint32_t& r0, uint32_t& r1, uint32_t& r2, uint32_t& r3) {
  asm volatile("ldmatrix.sync.aligned.m8n8.x4.trans.shared.b16 {%0,%1,%2,%3}, [%4];" : "=r"(r0), "=r"(r1), "=r"(r2), "=r"(r3) : "r"(addr) : "memory");
}
__device__ __forceinline__ void stsm_x4(uint32_t addr, uint32_t r0, uint32_t r1, uint32_t r2, uint32_t r3) {
  asm volatile("stmatrix.sync.aligned.m8n8.x4.shared.b16 [%0], {%1,%2,%3,%4};" :: "r"(addr), "r"(r0), "r"(r1), "r"(r2), "r"(r3) : "memory");
}
__device__ __forceinline__ void stsm_x4_t(uint32_t addr, uint32_t r0, uint32_t r1, uint32_t r2, uint32_t r3) {
  asm volatile("stmatrix.sync.aligned.m8n8.x4.trans.shared.b16 [%0], {%1,%2,%3,%4};" :: "r"(addr), "r"(r0), "r"(r1), "r"(r2), "r"(r3) : "memory");
}
__device__ __forceinline__ void sts128(uint32_t addr, uint32_t a, uint32_t b, uint32_t c, uint32_t d) {
  asm volatile("st.shared.v4.u32 [%0], {%1,%2,%3,%4};" :: "r"(addr), "r"(a), "r"(b), "r"(c), "r"(d) : "memory");
}
__device__ __forceinline__ float lds32f(uint32_t addr) {
  float v;
  asm volatile("ld.shared.f32 %0, [%1];" : "=f"(v) : "r"(addr) : "memory");
  return v;
}
__device__ __forceinline__ void sts32f(uint32_t addr, float a) {
  asm volatile("st.shared.f32 [%0], %1;" :: "r"(addr), "f"(a) : "memory");
}
__device__ __forceinline__ void mma_bf16(float (&c)[4], uint32_t a0, uint32_t a1, uint32_t a2, uint32_t a3, uint32_t b0, uint32_t b1) {
  asm volatile("mma.sync.aligned.m16n8k16.row.col.f32.bf16.bf16.f32 {%0,%1,%2,%3}, {%4,%5,%6,%7}, {%8,%9}, {%0,%1,%2,%3};"
               : "+f"(c[0]), "+f"(c[1]), "+f"(c[2]), "+f"(c[3]) : "r"(a0), "r"(a1), "r"(a2), "r"(a3), "r"(b0), "r"(b1));
}
__device__ __forceinline__ void mma_bf16_z(float (&c)[4], uint32_t a0, uint32_t a1, uint32_t a2, uint32_t a3, uint32_t b0, uint32_t b1) {
  asm volatile("mma.sync.aligned.m16n8k16.row.col.f32.bf16.bf16.f32 {%0,%1,%2,%3}, {%4,%5,%6,%7}, {%8,%9}, {%10,%10,%10,%10};"
               : "=f"(c[0]), "=f"(c[1]), "=f"(c[2]), "=f"(c[3]) : "r"(a0), "r"(a1), "r"(a2), "r"(a3), "r"(b0), "r"(b1), "f"(0.f));
}
__device__ __forceinline__ uint32_t movm_t(uint32_t v) {
  uint32_t r;
  asm volatile("movmatrix.sync.aligned.m8n8.trans.b16 %0, %1;" : "=r"(r) : "r"(v));
  return r;
}
__device__ __forceinline__ uint32_t pack_bf16(float lo, float hi) {
  uint32_t r;
  asm("cvt.rn.bf16x2.f32 %0, %1, %2;" : "=r"(r) : "f"(hi), "f"(lo));
  return r;
}
__device__ __forceinline__ float bf_lo(uint32_t v) { return __uint_as_float(v << 16); }
__device__ __forceinline__ float bf_hi(uint32_t v) { return __uint_as_float(v & 0xFFFF0000u); }
__device__ __forceinline__ void split3(float x, uint32_t& h, uint32_t& m, uint32_t& l) {
  h = pack_bf16(x, 0.f); x -= bf_lo(h);
  m = pack_bf16(x, 0.f); x -= bf_lo(m);
  l = pack_bf16(x, 0.f);
}
__device__ __forceinline__ float ex2(float x) { float r; asm("ex2.approx.ftz.f32 %0, %1;" : "=f"(r) : "f"(x)); return r; }
__device__ __forceinline__ float rcp_fast(float x) { float r; asm("rcp.approx.ftz.f32 %0, %1;" : "=f"(r) : "f"(x)); return r; }
__device__ __forceinline__ void red_v4(float* p, float a, float b, float c, float d) {
  asm volatile("red.global.add.v4.f32 [%0], {%1, %2, %3, %4};" :: "l"(p), "f"(a), "f"(b), "f"(c), "f"(d) : "memory");
}
__device__ __forceinline__ uint4 ld_ll(const uint4* p) {
  uint4 v;
  asm volatile("{\n.reg .b64 a, b;\nld.relaxed.gpu.global.v2.b64 {a, b}, [%4];\nmov.b64 {%0, %1}, a;\nmov.b64 {%2, %3}, b;\n}\n"
               : "=r"(v.x), "=r"(v.y), "=r"(v.z), "=r"(v.w) : "l"(p) : "memory");
  return v;
}
__device__ __forceinline__ void st_b64(uint2* p, uint32_t a, uint32_t b) {
  asm volatile("{\n.reg .b64 v;\nmov.b64 v, {%1, %2};\nst.relaxed.gpu.global.b64 [%0], v;\n}\n" :: "l"(p), "r"(a), "r"(b) : "memory");
}
__device__ __forceinline__ void st_b128(uint4* p, uint32_t a, uint32_t b, uint32_t c, uint32_t d) {
  asm volatile("{\n.reg .b128 v;\nmov.b128 v, {%1, %2, %3, %4};\nst.relaxed.gpu.global.b128 [%0], v;\n}\n" :: "l"(p), "r"(a), "r"(b), "r"(c), "r"(d) : "memory");
}
__device__ __forceinline__ uint4 ld_b128(const uint4* p) {
  uint4 v;
  asm volatile("{\n.reg .b128 v;\nld.relaxed.gpu.global.b128 v, [%4];\nmov.b128 {%0, %1, %2, %3}, v;\n}\n" : "=r"(v.x), "=r"(v.y), "=r"(v.z), "=r"(v.w) : "l"(p) : "memory");
  return v;
}

constexpr float LOG2E = 1.4426950408889634f;

struct Params {
  const __nv_bfloat16* wA_o;
  const __nv_bfloat16* wB_qkv;
  const __nv_bfloat16* wB_o;
  const unsigned* epoch;
  __nv_bfloat16* out;
};

#define ACC_DEF(d, n) _Pragma("unroll") for (int i_ = 0; i_ < (n); i_++) asm volatile("" : "=f"(d[i_]))
#define ACC_FENCE(d, n) _Pragma("unroll") for (int i_ = 0; i_ < (n); i_++) asm volatile("" : "+f"(d[i_]) :: "memory")
#define PIN(a, n) _Pragma("unroll") for (int i_ = 0; i_ < (n); i_++) asm volatile("" : "+f"((a)[i_]))
#define PINU(a, n) _Pragma("unroll") for (int i_ = 0; i_ < (n); i_++) asm volatile("" : "+r"((a)[i_]))

#define V_ADDR(p0, sw) uint32_t va_[2] = {(p0) + (srowoff >> 1) + (lhi ^ lsw2 ^ (sw)), (p0) + (srowoff >> 1) + ((32 + lhi) ^ lsw2 ^ (sw))}
#define STAGE_V(acc) { \
    _Pragma("unroll") for (int j_ = 0; j_ < 4; j_++) { \
      const float* a_ = (acc) + j_ * 8; \
      stsm_x4(va_[j_ & 1] + (j_ >> 1) * 8192, \
              pack_bf16(rs0 * a_[0], rs0 * a_[1]), pack_bf16(rs1 * a_[2], rs1 * a_[3]), pack_bf16(rs0 * a_[4], rs0 * a_[5]), pack_bf16(rs1 * a_[6], rs1 * a_[7])); } }
#define FRAG(dst, acc, TR, grp) { \
    _Pragma("unroll") for (int i_ = 15; i_ >= 0; i_--) { \
      const float r_ = (i_ & 8) ? rs1 : rs0; \
      const uint32_t w_ = pack_bf16(r_ * (acc)[4 * (i_ & 7) + (i_ >> 3) * 2], r_ * (acc)[4 * (i_ & 7) + (i_ >> 3) * 2 + 1]); \
      (dst)[8 + i_] = (TR) ? movm_t(w_) : w_; \
      if (i_ == 8 && warp >= 6 && mm < 15) { \
        _Pragma("unroll") for (int j_ = 0; j_ < 2; j_++) \
          st_b128(g_halo + (size_t)(mm * 8 + jj) * 512 + ((grp) * 4 + warp * 2 - 12 + j_) * 32 + lane, ((dst)[16 + j_ * 4] & ~1u) | H_BIT(l), (dst)[17 + j_ * 4], (dst)[18 + j_ * 4], (dst)[19 + j_ * 4]); } } \
    PINU((dst) + 8, 16); }
#define FRAG_PUT(src, slot) if (warp < 6) { _Pragma("unroll") for (int j_ = 0; j_ < 2; j_++) \
      sts128(sbase + OFF_S + (slot) * 8192 + 2048 + warp * 1024 + j_ * 512 + lane * 16, (src)[j_ * 4], (src)[j_ * 4 + 1], (src)[j_ * 4 + 2], (src)[j_ * 4 + 3]); }
#define FRAG_GET(dst, slot) { _Pragma("unroll") for (int j_ = 0; j_ < 2; j_++) \
      asm volatile("ld.shared.v4.u32 {%0, %1, %2, %3}, [%4];" : "=r"((dst)[j_ * 4]), "=r"((dst)[j_ * 4 + 1]), "=r"((dst)[j_ * 4 + 2]), "=r"((dst)[j_ * 4 + 3]) \
                   : "r"(sbase + OFF_S + (slot) * 8192 + warp * 1024 + j_ * 512 + lane * 16) : "memory"); }
#define RW(j) (((j) >> 1) * 4 + ((j) & 1))
template <int POS> __device__ __forceinline__ float exps16_(float* o, const float* p) {
  float s[4];
#pragma unroll
  for (int j = 0; j < 16; j++) { o[j] = ex2(POS ? p[RW(j)] : -p[RW(j)]); if (j < 4) s[j] = o[j]; else s[j & 3] += o[j]; }
  const float r = (s[0] + s[1]) + (s[2] + s[3]);
  return r + __shfl_xor_sync(0xffffffffu, r, 1);
}
template <int POS> __device__ __forceinline__ void exps16_fix(float* o, const float* p, float& sum) {
  if (__builtin_expect(__any_sync(0xffffffffu, !(sum > SUMLO && sum < SUMHI)), 0)) {
    float m = p[0], q[32];
#pragma unroll
    for (int j = 1; j < 16; j++) m = POS ? fmaxf(m, p[RW(j)]) : fminf(m, p[RW(j)]);
    const float x = __shfl_xor_sync(0xffffffffu, m, 1);
    m = POS ? fmaxf(m, x) : fminf(m, x);
#pragma unroll
    for (int j = 0; j < 16; j++) q[RW(j)] = p[RW(j)] - m;
    sum = exps16_<POS>(o, q);
  }
}
__device__ __forceinline__ void store16(const float* e, float sum, uint32_t dst, uint32_t dsw, int c0) {
  const float inv = rcp_fast(sum);
#pragma unroll
  for (int j = 0; j < 2; j++)
    sts128(dst + (((c0 + j) << 4) ^ dsw), pack_bf16(e[j * 8] * inv, e[j * 8 + 1] * inv), pack_bf16(e[j * 8 + 2] * inv, e[j * 8 + 3] * inv),
           pack_bf16(e[j * 8 + 4] * inv, e[j * 8 + 5] * inv), pack_bf16(e[j * 8 + 6] * inv, e[j * 8 + 7] * inv));
}
template <int POS> __device__ __forceinline__ void expp16(uint32_t* o, float* p) {
  {
#pragma unroll
    for (int r = 0; r < 4; r += 2) {
      float m = p[r];
#pragma unroll
      for (int j = 1; j < 8; j++) m = POS ? fmaxf(m, p[r + RW(j)]) : fminf(m, p[r + RW(j)]);
#pragma unroll
      for (int s = 1; s <= 2; s <<= 1) { const float x = __shfl_xor_sync(0xffffffffu, m, s); m = POS ? fmaxf(m, x) : fminf(m, x); }
#pragma unroll
      for (int j = 0; j < 8; j++) p[r + RW(j)] -= m;
    }
  }
#pragma unroll
  for (int j = 0; j < 8; j++) o[j] = pack_bf16(ex2(POS ? p[2 * j] : -p[2 * j]), ex2(POS ? p[2 * j + 1] : -p[2 * j + 1]));
}
__device__ __forceinline__ void scale32(float* o, const float* p, float c0, float c1) {
#pragma unroll
  for (int i = 0; i < 32; i++) asm volatile("mul.f32 %0, %1, %2;" : "=f"(o[i]) : "f"(p[i]), "f"((i & 2) ? c1 : c0));
}
__device__ __forceinline__ bool any_big(const float* p) {
  float m[4];
#pragma unroll
  for (int i = 0; i < 32; i++) m[i >> 3] = (i & 7) ? fmaf(p[i], p[i], m[i >> 3]) : p[i] * p[i];
  return __any_sync(0xffffffffu, !(fmaxf(fmaxf(m[0], m[1]), fmaxf(m[2], m[3])) < BIGLIM));
}
__device__ __forceinline__ void phiq_a(float* p, bool big) {
  if (__builtin_expect(!big, 1)) {
#pragma unroll
    for (int j = 0; j < 16; j++) p[j] = ex2(p[j]);
  }
}
template <int NEXT> __device__ __forceinline__ void phiq_b(uint32_t* o, float* p, bool big) {
  if (__builtin_expect(big, 0)) {
    expp16<0>(o, p); expp16<1>(o + 8, p);
  } else {
    if (NEXT) phiq_a(p + 16, false);
#pragma unroll
    for (int j = 0; j < 4; j++) {
      const float a = p[4 * j], b = p[4 * j + 1], c = p[4 * j + 2], d = p[4 * j + 3];
      const float ab = a * b, cd = c * d, r = rcp_fast(ab * cd), x = r * cd, y = r * ab;
      o[2 * j] = pack_bf16(x * b, x * a); o[2 * j + 1] = pack_bf16(y * d, y * c);
      o[8 + 2 * j] = pack_bf16(a, b); o[9 + 2 * j] = pack_bf16(c, d);
    }
  }
}
#define SCHED_FENCE() asm volatile("pmevent 0;" ::: "memory")

__global__ void __cluster_dims__(2, 1, 1) __launch_bounds__(384, 1)
mega_kernel(const Params prm  , const __grid_constant__ CUtensorMap tm_x0, const __grid_constant__ CUtensorMap tm_os,
            const __grid_constant__ CUtensorMap tm_o, const __grid_constant__ CUtensorMap tm_wf,
            const __grid_constant__ CUtensorMap tm_wqA, const __grid_constant__ CUtensorMap tm_wqB,
            const __grid_constant__ CUtensorMap tm_woA, const __grid_constant__ CUtensorMap tm_woB,
            const __grid_constant__ CUtensorMap tm_phi) {
  extern __shared__ __align__(1024) uint8_t smem_raw[];
  const uint32_t sbase = smem_u32(smem_raw);
  const uint32_t bar_full = sbase + OFF_BAR;
  const uint32_t bar_done = bar_full + 384;
  const uint32_t bar_stat = bar_full + 768, bar_stat2 = bar_full + 776, bar_epi = bar_full + 784, bar_phi = bar_full + 936  , bar_halo = bar_full + 904  ;
  const uint32_t bar_xr = bar_full + 800, bar_lx = bar_full + 808, bar_stg = bar_full + 832;
  const uint32_t bar_chk = bar_full + 848;

  const int warp = __shfl_sync(0xffffffffu, threadIdx.x >> 5, 0), lane = threadIdx.x & 31;
  const uint32_t bar_kx = sbase + OFF_ID + 384 + warp * 8;
  uint32_t rank;
  asm volatile("mov.u32 %0, %%cluster_ctarank;" : "=r"(rank));
  const int aux = (int)blockIdx.x - NMAIN, tp = (int)(blockIdx.x >> 1) - 4;
  const int gp = tp < 0 ? 0 : (tp < 32 ? tp & 7 : 1 + (tp - 32) % 7), me = tp < 0 ? tp + 8 : (tp < 32 ? tp >> 3 : 4 + (tp - 32) / 7);
  const int jj = me, cc = gp;
  const int cta = aux >= 0 ? -1 : (cc * 8 + jj) * 2 + (int)rank;
  const int mm = cc * 2 + (int)rank;

#define LOAD_EPOCH() const unsigned epoch = ld_relaxed(prm.epoch), ep1 = epoch + 1; (void)epoch
  int budget = 1 << 22;
  unsigned epoch0 = 0;

  if (cta >= 0) {
    if (warp == 8 && elect_one()) {
#pragma unroll
      for (int u = 0; u < 2; u++) mbar_init(bar_full + u * 8, 1);
      asm volatile("fence.mbarrier_init.release.cluster;" ::: "memory");
      fence_proxy_async_smem();
#pragma unroll 1
      for (int u = 0; u < 2; u++) {
        const uint32_t fb = bar_full + u * 8;
        mbar_expect_tx(fb, QST + SLOT);
        tma_load_t(sbase + OFF_RA + u * SLOT, &tm_x0, fb, srcb(jj, u) * 128, mm * 128);
#pragma unroll
        for (int i = 0; i < 6; i++) tma_load_2d(sbase + u * QST + i * 4096, &tm_wqA, fb, jj * 128 + (i >> 1) * 1024, srcb(jj, u) * 128 + (i & 1) * 32);
        PROFT(472 + u);
      }
    }
    __syncwarp();
    if (elect_one()) {
#pragma unroll
      for (int i = 0; i < 4; i++) {
        const int u = warp * 4 + i;
        mbar_init(u < 2 ? bar_kx : bar_full + u * 8, ((u >= 4 && u < 11) || (u > 32 && u != 40)) ? 2 : 1); mbar_init(bar_done + u * 8, 16);
      }
      mbar_init(bar_stat + warp * 16, 0x111111181182ull >> (4 * warp) & 15);
      mbar_init(bar_stat + warp * 16 + 8, 0x111111121811ull >> (4 * warp) & 15);
      mbar_init(bar_chk + 112 + (warp & 7) * 8, 1);
      mbar_init(bar_kx, 1);
      asm volatile("fence.mbarrier_init.release.cluster;" ::: "memory");
    }
    __syncwarp();
    if (threadIdx.x == 383) epoch0 = ld_relaxed(prm.epoch);
    if (PRL == 0 && lane == 0 && warp >= 8) PROFT(440 + warp - 8);
    __syncthreads();
    if (PRL == 0 && threadIdx.x == 256) PROFT(444);
    asm volatile("barrier.cluster.arrive.relaxed.aligned;" ::: "memory");
  }

  if (cta < 0) {
    LOAD_EPOCH();
    const uint32_t buf = sbase + warp * SLOT, bar = sbase + OFF_BAR + warp * 16;
    const uint32_t lsw = (lane & 7) << 4, lhi = (lane >> 4) << 4, lrow = (lane & 15) * 128;
    const bool el = elect_one();
    if (el) {
      mbar_init(bar, 1); mbar_init(bar + 8, 1);
      asm volatile("fence.mbarrier_init.release.cluster;" ::: "memory");
    }
#pragma unroll 1
    for (int rd = 0; rd < (NLAYERS > 1 ? 5 : 2); rd++) {
      if (rd >= 2 && warp >= 8) break;
      const int tk = rd < 2 ? aux * 12 + warp : aux * 8 + warp;
      const int half = tk & 1;
      const int blk = rd < 2 ? (tk >> 1) * 2 + rd : (4 - rd) * 16 + (tk >> 1);
      const CUtensorMap* tm = rd < 2 ? &tm_wqA : (rd == 2 ? &tm_wqB : &tm_wf);
      const int j0 = (blk & 15) >> 1;
#define AUX_LOAD(n) { const uint32_t d_ = buf + ((n) & 1) * 8192, b_ = bar + ((n) & 1) * 8; const int r_ = kslice(j0, 2 * ((AUXORD >> (4 * (n))) & 7) + half) * 64; \
        mbar_expect_tx(b_, 8192); tma_load_2d(d_, tm, b_, blk * 64, r_); tma_load_2d(d_ + 4096, tm, b_, blk * 64, r_ + 32); }
      if (el) {
        if (rd == 3) { wait_flag(&g_flags.wfready[j0].v, ep1 * 16); fence_proxy_async_global(); }
        AUX_LOAD(0); AUX_LOAD(1);
      }
      __syncwarp();
      float cs[8][4];
#pragma unroll
      for (int i = 0; i < 8; i++) cs[i][0] = cs[i][1] = cs[i][2] = cs[i][3] = 0.f;
#pragma unroll 1
      for (int n = 0; n < 8; n++) {
        const uint32_t tb = buf + (n & 1) * 8192 + lrow;
        mbar_wait(bar + (n & 1) * 8, (n >> 1) & 1);
#pragma unroll
        for (int i = 0; i < 16; i++) {
          uint32_t b0, b1, b2, b3;
          ldsm_x4_t(tb + (i >> 2) * 2048 + (((i & 3) * 32 + lhi) ^ lsw), b0, b1, b2, b3);
          mma_bf16(cs[2 * (i & 3)], 0x3F803F80u, 0x3F803F80u, 0x3F803F80u, 0x3F803F80u, b0, b1);
          mma_bf16(cs[2 * (i & 3) + 1], 0x3F803F80u, 0x3F803F80u, 0x3F803F80u, 0x3F803F80u, b2, b3);
        }
        __syncwarp();
        if (el && n < 6) AUX_LOAD(n + 2);
        __syncwarp();
      }
      if (lane < 4) {
#pragma unroll
        for (int i = 0; i < 8; i++) st_b64(&g_colsum[rd >= 2][blk * 32 + i * 4 + lane][half], __float_as_uint(cs[i][0]), (__float_as_uint(cs[i][1]) & ~3u) | (ep1 & 3));
      }
      __syncwarp();
    }
  } else if (warp >= 8) {
    asm volatile("setmaxnreg.dec.sync.aligned.u32 40;");
    if (warp == 8) {
      const bool el = elect_one();
      cluster_wait();
      if (el) {
        if (PRL == 0) PROFT(445);
#pragma unroll 1
        for (int l = 0; l < NLAYERS; l++) {
          const uint32_t par = l & 1;
          const CUtensorMap* tqk = par ? &tm_wf : &tm_wqA;
          const CUtensorMap* tv = par ? &tm_wqB : &tm_wqA;
          const CUtensorMap* two = par ? &tm_woB : &tm_woA;
          if (l == 1) { LOAD_EPOCH(); wait_flag(&g_flags.wfready[jj].v, ep1 * 16); fence_proxy_async_global(); }
#pragma unroll 1
          for (int u = l ? 0 : EARLY; u < 32; u++) {
            const uint32_t fb = bar_full + u * 8;
            const int v = (l || u > 7) ? u : u - 4;
            const bool res = u < 11 || (u >= 18 && u < 22);
            mbar_expect_tx(fb, res ? QST : QST + SLOT);
            const int row = kslice(jj, v < 4 ? v & 1 : (u < 18 ? u - 2 : (u < 22 ? u - 6 : u - 20))) * 64 + (int)rank * 32;
            const int ps = v < 4 ? v >> 1 : (u >= 18), col = jj * 128 + ps * 64;
            const int c0 = par ? jj * 128 + (ps ? 0 : 1024) : col;
            const uint32_t dst = sbase + (u & 3) * QST + rank * 4096;
            uint32_t op[7] = {dst, dst + 8192, dst + 16384, (uint32_t)c0, (uint32_t)(c0 + (par ? 64 : 1024)), (uint32_t)(col + 2048), (uint32_t)row};
            PINU(op, 7);
            mbar_wait_sl(bar_done + (u >= 4 ? u - 4 : 43 + u + (u >> 1)) * 8, par ^ (u < 4));
            tma_load_2d_mc(op[0], tqk, fb, op[3], op[6]);
            tma_load_2d_mc(op[1], tqk, fb, op[4], op[6]);
            tma_load_2d_mc(op[2], tv, fb, op[5], op[6]);

            if (u < 8) PROFL3(472 + u);
          }
#pragma unroll 1
          for (int s = 0; s < 16; s++) {
            const uint32_t fb = bar_full + (32 + s) * 8;
            const int ts = s + 1;
            const bool ot = s >= 5 && ts < 8;
            mbar_expect_tx(fb, SLOT);
            uint32_t op[4] = {sbase + rank * 8192 + (uint32_t)((WO_BSLOT >> (4 * s)) & 15) * SLOT, (uint32_t)wslice(jj, s) * 64,
                              sbase + (uint32_t)((WO_ASLOT(par) >> (4 * ts)) & 15) * SLOT, (uint32_t)wslice(jj, ts) * 64};
            PINU(op, 4);
            mbar_wait_sl(bar_done + (28 + (uint32_t)((0xDCCBA98765433110ull >> (4 * s)) & 15)) * 8, par);
            tma_load_2d_mc(op[0], two, fb, jj * 128 + (int)rank * 64, op[1]);
            if (ot) {
              mbar_expect_tx(bar_chk - 8 + ts * 8, SLOT);
              tma_load_t(op[2], &tm_o, bar_chk - 8 + ts * 8, op[3], mm * 128);
            }
          }
        }
      }
      __syncwarp();
    } else if (warp == 9) {
      const bool el = elect_one();
      if (el) {
#pragma unroll
        for (int i = 0; i < 2; i++) {
          mbar_expect_tx(bar_full + 32 + i * 8, SLOT);
          mbar_wait_sl(bar_full + (i ? OWNW1 : OWNW0) * 8, 0);
          tma_load_t(sbase + OFF_S + i * SLOT, &tm_x0, bar_full + 32 + i * 8, jj * 128 + i * 64, mm * 128);
        }
      }
      __syncwarp();
      LOAD_EPOCH();
#pragma unroll 1
      for (int lp = 0; lp < 4 * NLAYERS; lp++) {
        const int l = lp >> 2, ph = lp & 3;
        if (ph == 3) continue;
        const uint32_t par = l & 1;
        const unsigned* pp = reinterpret_cast<const unsigned*>(g_obuf + (ph >> 1) * 64 + (size_t)(mm * 128 + (ph ? 0 : S_LEN) + ((lane & 7) | PROWS) * 16 + (jj & 1) * 8) * D_MODEL +
                                                               (jj >> 1) * 16 + srcb(jj, lane >> 3) * 128);
        const CUtensorMap* tm = lp ? &tm_o : &tm_x0;
        const int row = mm * 128 + ((ph || !l) ? 0 : S_LEN);
        const uint32_t bit = ph ? O_BIT(l) : X_BIT(l - 1);
        const uint32_t slots = ph ? (uint32_t)(WO_ASLOT(par) >> (ph * 32 - 28)) : 0x8769876u;
        const unsigned long long fr = ph == 0 ? XPACE : ph == 1 ? (par ? FRB : 0x35351F1E1Dull) : 0x27262524232232ull;
        uint32_t no = (lp == 0 || (lp & 7) == 1) ? 0 : (ph == 1 ? NOB : (ph ? NO1 : NOX)), v0 = 0, v1 = 0;
        mbar_wait_sl(ph ? bar_done + ((uint32_t)fr & 63) * 8 : (l ? bar_done + 47 * 8 : bar_full), ph ? par : (l ? par ^ 1 : 0));
        if (el && ph) PROFT(324 + l * 16 + ph);
        __syncwarp();
        if (no && (ph == 1 ? SPD1 : (ph ? SPD2 : SPD0))) __nanosleep(ph == 1 ? SPD1 : (ph ? SPD2 : SPD0));
        if (no) { v0 = ld_relaxed(pp); if (ph != 1) __nanosleep(POLLGAP); v1 = ld_relaxed(pp); }
#pragma unroll 1
        for (int i = lp ? 0 : 4; i < (ph == 1 ? 5 : 7); i++, no >>= 8) {
          uint32_t op[4] = {(lp ? bar_chk + (ph >> 1) * 112 : bar_full + 32) + i * 8  , sbase + ((slots >> (4 * i)) & 15) * SLOT,
                            (uint32_t)(srcb(jj, i) * 128 + (ph >> 1) * 64), bar_done + ((uint32_t)(fr >> (8 * i)) & 63) * 8};
          PINU(op, 4);
          if (el) mbar_expect_tx(op[0], SLOT);
#pragma unroll 1
          for (int it = 0; (no & 0xFF) && it < (1 << 18); it++) {
            no &= __ballot_sync(0xffffffffu, (v0 ^ bit) & 1) >> (8 * i);
            if (no) v0 = ld_relaxed(pp);
            if (!(no & 0xFF)) break;
            no &= __ballot_sync(0xffffffffu, (v1 ^ bit) & 1) >> (8 * i);
            if (no) v1 = ld_relaxed(pp);
          }
          if (i >= (ph ? 1 : 4)) mbar_wait_sl(op[3], par);
          if (el) {
            if (i == 0) PROFT(320 + l * 16 + ph);
            PROFL3(448 + ph * 8 + i);
            tma_load_t(op[1], tm, op[0], op[2], row);
          }
          __syncwarp();
        }
        if (ph == 0 && el) {
          if (l) { wait_flag(&g_flags.xready[l][mm].v, ep1 * 8); fence_proxy_async_global(); }
#pragma unroll 1
          for (int u = 11; u < 34; u++) {
            if (u == 18) u = 22;
            if (u == 32) mbar_expect_tx(bar_xr, 2 * SLOT);
            uint32_t op[3] = {sbase + OFF_RA + (u & 3) * SLOT, u < 32 ? bar_full + u * 8 : bar_xr, (uint32_t)kslice(jj, u < 18 ? u - 2 : (u < 32 ? u - 20 : u - 32)) * 64};
            PINU(op, 3);
            mbar_wait_sl(bar_done + (u - 4) * 8, par);
            tma_load_t(op[0], tm, op[1], op[2], row);
          }
        }
        __syncwarp();
      }
      if (el && atomicAdd(&g_flags.done.v, 1) == ep1 * NMAIN - 1) asm volatile("st.relaxed.gpu.global.u32 [%0], %1;" :: "l"(&g_flags.epoch.v), "r"(ep1) : "memory");
      __syncwarp();
      cluster_wait();
    } else {
      const int hw = warp - 10;
      if (hw == 0 && elect_one()) {
#pragma unroll 1
        for (int u = 2; u < 4; u++) {
          const uint32_t fb = bar_full + u * 8;
          mbar_expect_tx(fb, QST + SLOT);
          tma_load_t(sbase + OFF_RA + u * SLOT, &tm_x0, fb, srcb(jj, u) * 128, mm * 128);
#pragma unroll
          for (int i = 0; i < 6; i++) tma_load_2d(sbase + u * QST + i * 4096, &tm_wqA, fb, jj * 128 + (i >> 1) * 1024, srcb(jj, u) * 128 + (i & 1) * 32);
          mbar_arrive_local(fb + 32);
        }
      }
      __syncwarp();
      const unsigned epoch = hw ? __shfl_sync(0xffffffffu, epoch0, 31) : ld_relaxed(prm.epoch), ep1 = epoch + 1;
      const bool el = elect_one();
      cluster_wait();
      if (hw == 0) {
        mbar_wait_sl(bar_full + 8, 0);
        if (lane < 7) prefetch_tmap(lane == 0 ? &tm_os : lane == 1 ? &tm_o : lane == 2 ? &tm_wf : lane == 3 ? &tm_wqB : lane == 4 ? &tm_woA : lane == 5 ? &tm_woB : &tm_phi);
#pragma unroll 1
        for (int i = 0; i < (NLAYERS > 1 ? 5 : 0); i++) {
          if (i == 0) mbar_wait_sl(bar_done + FD0 * 8, 0);
          if (el) {
            if (i == 0) { mbar_expect_tx(bar_phi, 2 * SLOT + 8192); tma_load_2d(sbase + OFF_PHI, &tm_phi, bar_phi, 0, jj * 128); }
            else tma_load_2d(sbase + 12 * SLOT - 4096 + i * 4096, &tm_wqB, bar_phi, jj * 128 + ((i - 1) >> 1) * 64, mm * 64 + (~i & 1) * 32);
          }
          __syncwarp();
          __nanosleep(PFGAP);
        }
      } else {
        if (lane < 24) {
          const uint32_t one = (lane & 8) ? 0u : 0x3F80u << ((lane & 1) * 16), w = (lane >> 1) & 3;
          sts128(sbase + OFF_ID + lane * 16, w == 0 ? one : 0u, w == 1 ? one : 0u, w == 2 ? one : 0u, w == 3 ? one : 0u);
        }
#pragma unroll 1
        for (int b = 0; b < 2; b++) {
          float4* z = reinterpret_cast<float4*>(g_kv[b] + (jj * 4) * KVH + mm * (4 * KVH / 16)) + lane;
#pragma unroll
          for (int i = 0; i < 6; i++) z[i * 32] = make_float4(0.f, 0.f, 0.f, 0.f);
        }
#pragma unroll 1
        for (int i = 0; i < 16; i++) {
          const int b = i >> 2;
          const uint32_t v = (b == 0 ? O_BIT(0) : b == 1 ? X_BIT(0) : H_BIT(0)) + 1;
          uint4* p = b < 2 ? reinterpret_cast<uint4*>(g_obuf + (size_t)(b * S_LEN + mm * 128 + (i & 3) * 32 + (lane >> 3) * 8) * D_MODEL + jj * 128 + (b ? 0 : 64)) + (lane & 7)
                           : g_halo + (size_t)(mm * 8 + jj) * 512 + i * 32 + lane;
          *p = make_uint4(v, v, v, v);
        }
        fence_proxy_async_global();
      }
      __syncwarp();
      uint32_t chkp = 0;
#pragma unroll 1
      for (int lp = 0; lp < 8 * NLAYERS; lp++) {
        const int l = lp >> 3, tk = lp & 7, ph = tk ? 2 - hw : 0;
        const uint32_t par = l & 1;
        int lane; asm volatile("mov.u32 %0, %%laneid;" : "=r"(lane));
        if (tk == 5 || (hw && tk == 0 && l)) {
          const uint32_t bit = ph ? O_BIT(l) : X_BIT(l - 1);
          uint32_t slots = ph ? (uint32_t)(WO_ASLOT(par) >> (ph * 32 - 28)) : 0x8769876u;
          const uint32_t a0 = sbase + (lane & 7) * 126 + lane * 4 + (lane & 1) * 14;
#pragma unroll 1
          for (int c = 0; c < 7; c++, slots >>= 4) {
            const uint32_t cb = bar_chk + 112 - hw * 112 + c * 8;
#pragma unroll 1
            for (int it = 0; it < (1 << 12); it++) {
              mbar_wait_sl(cb, (chkp >> c) & 1);
              chkp ^= 1u << c;
              if (el) PROFL3(384 + ph * 8 + c);
              uint32_t bad;
              asm volatile("{\n.reg .b32 w<16>;\n"
                           "ld.shared.u32 w0, [%1 + 0];\n"
                           "ld.shared.u32 w1, [%1 + 1024];\n"
                           "ld.shared.u32 w2, [%1 + 2048];\n"
                           "ld.shared.u32 w3, [%1 + 3072];\n"
                           "ld.shared.u32 w4, [%1 + 4096];\n"
                           "ld.shared.u32 w5, [%1 + 5120];\n"
                           "ld.shared.u32 w6, [%1 + 6144];\n"
                           "ld.shared.u32 w7, [%1 + 7168];\n"
                           "ld.shared.u32 w8, [%1 + 8192];\n"
                           "ld.shared.u32 w9, [%1 + 9216];\n"
                           "ld.shared.u32 w10, [%1 + 10240];\n"
                           "ld.shared.u32 w11, [%1 + 11264];\n"
                           "ld.shared.u32 w12, [%1 + 12288];\n"
                           "ld.shared.u32 w13, [%1 + 13312];\n"
                           "ld.shared.u32 w14, [%1 + 14336];\n"
                           "ld.shared.u32 w15, [%1 + 15360];\n"
                           "lop3.b32 w0, w0, w1, %2, 0x7E;\n"
                           "lop3.b32 w2, w2, w3, %2, 0x7E;\n"
                           "lop3.b32 w4, w4, w5, %2, 0x7E;\n"
                           "lop3.b32 w6, w6, w7, %2, 0x7E;\n"
                           "lop3.b32 w8, w8, w9, %2, 0x7E;\n"
                           "lop3.b32 w10, w10, w11, %2, 0x7E;\n"
                           "lop3.b32 w12, w12, w13, %2, 0x7E;\n"
                           "lop3.b32 w14, w14, w15, %2, 0x7E;\n"
                           "lop3.b32 w0, w0, w2, w4, 0xFE;\nlop3.b32 w6, w6, w8, w10, 0xFE;\nlop3.b32 w0, w0, w12, w14, 0xFE;\nlop3.b32 %0, w0, w6, 1, 0xA8;\n}\n"
                           : "=r"(bad) : "r"(a0 + (slots & 15) * SLOT), "r"(bit) : "memory");
              if (__all_sync(0xffffffffu, bad == 0)) break;
              if (el) {
                fence_proxy_async_smem();
                mbar_expect_tx(cb, SLOT);
                tma_load_t(sbase + (slots & 15) * SLOT, &tm_o, cb, srcb(jj, c) * 128 + (ph >> 1) * 64, mm * 128 + (ph ? 0 : S_LEN));
                RETRY_COUNT();
              }
              __syncwarp();
            }
            if (el) { mbar_arrive_local(bar_full + (c + (ph ? 25 + ph * 8 : 4)) * 8); PROFL3(416 + ph * 8 + c); PROF2V(); }
            __syncwarp();
          }
        } else if (hw && (tk & 5) == 1) {
          {
            const int hp = tk >> 1;
            const uint4* src = reinterpret_cast<const uint4*>(g_colsum[par][jj * 64 + hp * 32 + lane]);
            uint32_t bad;
            int it = 0;
            float c[6];
            do {
              bad = 0;
#pragma unroll
              for (int p = 0; p < 3; p++) {
                const uint4 v = ld_ll(src + ((par && p < 2) ? (hp ? -32 : 512) + p * 32 : p * 512));
                bad |= (v.y ^ ep1) | (v.w ^ ep1);
                c[2 * p] = __uint_as_float(v.x) + __uint_as_float(v.z); c[2 * p + 1] = __uint_as_float(v.y) + __uint_as_float(v.w);
              }
              bad &= 3;
              if (bad) __nanosleep(CSGAP);
            } while (bad && ++it < (1 << 16));
#pragma unroll
            for (int p = 0; p < 6; p++) {
              uint32_t h, m, lo;
              split3(c[p], h, m, lo);
              sts128(sbase + OFF_LNB + hp * 4096 + (p >> 1) * 1024 + lane * 32 + (p & 1) * 16, h | (m << 16), h | (lo << 16), h | (m << 16), lo | (m << 16));
            }
            fence_proxy_async_smem();
            __syncwarp();
            if (el) { mbar_arrive_local(hp ? bar_stat2 : bar_stat); if (hp == 0) PROFT(324 + l * 16); }
            __syncwarp();
          }
        } else if (tk == 0) {
          mbar_wait_sl(bar_done + (l ? 24 : 56), par);
          const uint4* sp = reinterpret_cast<const uint4*>(g_stats + (size_t)(mm * 128) * 8) + lane;
          if (el) PROFL3(484);
#pragma unroll 1
          for (int hf = 2 * hw; hf < (l ? 4 : 2 + 2 * hw); hf++) {
            if (NLAYERS > 1 && l == 0 && el) tma_load_2d(sbase + 11 * SLOT + hf * 4096, &tm_wqB, bar_phi, 1024 + jj * 128 + (hf >> 1) * 64, mm * 64 + (hf & 1) * 32);
            __syncwarp();
            uint4 v[4];
            uint32_t bad;
            int it = 0;
            do {
              bad = 0;
#pragma unroll
              for (int i = 0; i < 4; i++) { v[i] = ld_ll(sp + (hf * 4 + i) * 32); bad |= (v[i].y ^ STAT_TAG(l)) | (v[i].w ^ STAT_TAG(l)); }
              bad &= 3;
              if (bad) __nanosleep(200);
            } while (bad && ++it < (1 << 16));
            __syncwarp();
            if (el) PROFL3(480 + hf);
            float mean = 0.f, m2 = 0.f;
#pragma unroll
            for (int i = 0; i < 4; i++) {
              float a = __uint_as_float(v[i].x) + __uint_as_float(v[i].z);
              a += __shfl_xor_sync(0xffffffffu, a, 1); a += __shfl_xor_sync(0xffffffffu, a, 2);
              a *= 0.125f;
              const float e0 = __uint_as_float(v[i].x) - a, e1 = __uint_as_float(v[i].z) - a;
              float q = fmaf(fmaf(e0, e0, e1 * e1), 128.f, __uint_as_float(v[i].y) + __uint_as_float(v[i].w));
              q += __shfl_xor_sync(0xffffffffu, q, 1); q += __shfl_xor_sync(0xffffffffu, q, 2);
              if ((lane & 3) == i) { mean = a; m2 = q; }
            }
            const uint32_t row = hf * 32 + (lane & 3) * 8 + (lane >> 2);
            uint32_t h, m, lo;
            split3(-0.5f * mean, h, m, lo);
            sts128(sbase + OFF_LNA + row * 16, h | (h << 16), m | (h << 16), lo | (m << 16), m | (lo << 16));
            sts32f(sbase + OFF_ST + row * 4, rsqrtf(m2 * (1.f / 1024.f) + 1e-5f));
          }
          if (hw) continue;
          fence_proxy_async_smem();
          __syncwarp();
          if (el) { mbar_arrive_local(bar_stat); PROFT(323 + l * 16); }
          __syncwarp();
#pragma unroll 1
          for (int i = 0; i < 8 - 4 * l; i++) {
            asm volatile("prefetch.global.L2 [%0];" :: "l"(i < 4 ? (l ? prm.wB_o : prm.wA_o) + (size_t)cta * 8192 + i * 2048 + lane * 64
                                                                 : prm.wB_qkv + (size_t)(cta * 8 + (i - 4) * 2 + (lane >> 4)) * 3072 + 2048 + (lane & 15) * 64));
            __nanosleep(PFGAP);
          }
        } else if (lp == 3) {
#pragma unroll 1
          for (int c = 0; c < (NLAYERS > 1 ? 8 : 0); c++) {
            if (!(c & 3)) { asm volatile("bar.sync %0, 288;" :: "r"(BAR_WF + (c >> 2)) : "memory"); fence_proxy_async_smem(); }
            if (el) {
              tma_store_2d(&tm_wf, sbase + 11 * SLOT + c * 4096, (c < 4 ? 1024 : -128) + jj * 128 + (c >> 1) * 64, mm * 64 + (c & 1) * 32);
              if (c == 7) {
                asm volatile("cp.async.bulk.commit_group;\ncp.async.bulk.wait_group.read 0;" ::: "memory");
                mbar_arrive_local(bar_phi + 8);
              } else __nanosleep(WFGAP);
            }
            __syncwarp();
          }
          if (el) { bulk_commit_wait(); signal_release(&g_flags.wfready[jj].v); PROFT(335); }
          __syncwarp();
        } else if (tk == 2 || tk == 4) {
          if (par) continue;
          const int i = tk >> 2;
          mbar_wait_sl(bar_done + (i ? HW1 : (hw ? 19 : HW0)) * 8, 0);
          const uint4* src = g_halo + (size_t)(mm * 8 + jj - 8) * 512 + i * 256 + hw * 128 + lane;
          uint4 v[4];
          int it = 0;
          bool ok;
          do {
#pragma unroll
            for (int j = 0; j < 4; j++) v[j] = mm ? ld_b128(src + j * 32) : make_uint4(H_BIT(l), 0, 0, 0);
            ok = __all_sync(0xffffffffu, (((v[0].x ^ H_BIT(l)) | (v[1].x ^ H_BIT(l)) | (v[2].x ^ H_BIT(l)) | (v[3].x ^ H_BIT(l))) & 1) == 0);
          } while (!ok && ++it < (1 << 16));
#pragma unroll
          for (int j = 0; j < 4; j++) sts128(sbase + OFF_S + hw * 8192 + j * 512 + lane * 16, v[j].x, v[j].y, v[j].z, v[j].w);
          __syncwarp();
          if (el) { mbar_arrive_local(bar_halo + hw * 8); PROFT(331 + l * 16 + i * 2 + hw); }
          __syncwarp();
        } else if (tk == 6 && hw == 0 && l < NLAYERS - 1) {
          bar_sync<BAR_X1, 288>();
          if (el) {
            PROFT(328 + l * 16);
            mbar_wait_sl(bar_full + XD * 8, par ^ 1);
            tma_store_t(&tm_o, sbase + 11 * SLOT, jj * 128 + 64, mm * 128 + S_LEN);
            bulk_commit_wait();
            signal_release(&g_flags.xready[l + 1][mm].v);
            PROFT(330 + l * 16);
          }
          __syncwarp();
        }
      }
    }
    cluster_sync();
  } else {
    asm volatile("setmaxnreg.inc.sync.aligned.u32 232;");
    const int wg = warp >> 2;
    const int r0 = warp * 16;
    const uint32_t pK = sbase + OFF_S, pV = sbase + OFF_S + SLOT;
#define PMASKS(on, bit) const uint32_t pm0 = ((on) && t == (g >> 1)), pbit = (bit)
#define PBIT(w) (((w) & ~pm0) | (pbit & pm0))
#define LANE_CONSTS() \
    int lane; asm volatile("mov.u32 %0, %%laneid;" : "=r"(lane)); \
    const int g = lane >> 2, t = lane & 3; \
    const uint32_t srowoff = (r0 + (lane & 15)) * 128, lsw = (lane & 7) << 4, lhi = (lane >> 4) << 4, lsw2 = (lane & 6) << 3; \
    (void)g; (void)t; (void)srowoff; (void)lsw; (void)lhi; (void)lsw2;
    uint32_t stgp = 0, peer;
    asm volatile("mapa.shared::cluster.u32 %0, %1, %2;" : "=r"(peer) : "r"(sbase), "r"(rank ^ 1));
    peer -= sbase;
    const uint32_t dA0 = (((sbase & 0x3FFFF) + wg * 8192) >> 4) | 0x10000u, dB0 = ((sbase & 0x3FFFF) >> 4) | 0x2000000u;
#define DESC(lo, hi) ((uint64_t)(uint32_t)(lo) | ((uint64_t)(hi) << 32))
#define STG_ARRIVE() { __syncwarp(); if (elect_one()) mbar_arrive_local(bar_stg); }
#define STG_WAIT() { mbar_wait(bar_stg, stgp); stgp ^= 1; }
#define PROFS() do {} while (0)
#define REL(addr) { if (elect_one()) { mbar_arrive_local(addr); asm volatile("mbarrier.arrive.shared::cluster.b64 _, [%0];" :: "r"((addr) + peer) : "memory"); } }
#define QSTEP(ACC, DA, SC) { \
      const uint32_t da = (DA), db = dB0 + (ub & 0x18) * (QST >> 7); \
      mbar_wait(ub, par); \
      wgmma_fence(); \
      wgmma4_n192<SC>(ACC, da, db); \
      wgmma_commit(); PROFS(); }
#define QREL() { wgmma_wait<1>(); REL(ub + 376); ub += 8; }
#define RA_CUR (dA0 + (OFF_RA >> 4) + (ub & 0x18) * (SLOT >> 7))
#define PUMP1() { QSTEP(S1, RA_CUR, 1); QREL(); }
#define PUMPN() { wgmma_fence(); wgmma4_n192<1>(S1, RA_CUR, dB0 + (ub & 0x18) * (QST >> 7)); wgmma_commit(); PROFS(); QREL(); }
#define PUMP0() { PUMP1(); SCHED_FENCE(); }
#define WSTEP() { \
      const uint32_t s4 = (ub - bar_full - 256) >> 1; \
      const uint32_t da = dA0 + (((uint32_t)(WO_ASLOT(par) >> s4) & 15) << 10), db = dB0 + (((uint32_t)(WO_BSLOT >> s4) & 15) << 10); \
      mbar_wait(ub, par); \
      wgmma_fence(); \
      wgmma4_n128<1>(S1, da, db); \
      wgmma_commit(); PROFS(); \
      wgmma_wait<1>(); \
      if (s4) REL(ub + 376); \
      ub += 8; }
#define PUMPS(n) { _Pragma("unroll 1") for (int i_ = 0; i_ < (n); i_++) PUMP1(); }
#define LNSTEP(ACC, hh) { wgmma_fence(); wgmma_n192<1, 0>(ACC, make_desc(sbase + OFF_LNA + wg * 1024, 0, 128) ^ (1ull << 62), make_desc(sbase + OFF_LNB + (hh) * 4096, 0, 128) ^ (1ull << 62)); }
#define WARP_STORE(tm, tile, col, row) { fence_proxy_async_smem(); __syncwarp(); WARP_STORE0(tm, tile, col, row); }
#define WARP_STORE0(tm, tile, col, row) { \
      if (elect_one()) { tma_store_2d(tm, (tile) + r0 * 128, col, (row) + r0); asm volatile("cp.async.bulk.commit_group;" ::: "memory"); } __syncwarp(); }
#define TILE_CONSTS(base, on, bit) \
      uint32_t ta[5]; \
      { PMASKS(on, bit); (void)pbit; ta[4] = pm0; } \
      _Pragma("unroll") for (int j = 0; j < 4; j++) ta[j] = (base) + srowoff + ((((uint32_t)j << 5) + lhi) ^ lsw); \
      PINU(ta, 5); SCHED_FENCE(); \
      const uint32_t pm0 = ta[4], pbit = (bit)
#define X_OUT(pc, W) { \
      _Pragma("unroll") for (int j = 0; j < 4; j++) \
        stsm_x4(ta[j] + (pc) * SLOT, \
                PBIT(pack_bf16((W)[j * 8 + 0], (W)[j * 8 + 1])), PBIT(pack_bf16((W)[j * 8 + 2], (W)[j * 8 + 3])), \
                (pack_bf16((W)[j * 8 + 4], (W)[j * 8 + 5])), (pack_bf16((W)[j * 8 + 6], (W)[j * 8 + 7]))); }
#define REST_P1(SKEW) { \
      mbar_wait(bar_stat2, par); \
      LNSTEP(S1, 1); \
      wgmma_commit(); \
      _Pragma("unroll 1") while (ub < bar_full + 256) { \
        const bool hold = ub == bar_full + 256 - 8 * (SKEW) && wg == 0; \
        if (hold) { wgmma_wait<0>(); REL(ub + 376); bar_sync<BAR_SKEW, 256>(); } \
        QSTEP(S1, RA_CUR, 1); \
        if (ub == bar_full + 248 && wg == 1) bar_arrive<BAR_SKEW, 256>(); \
        wgmma_wait<1>(); if (!hold) REL(ub + 376); ub += 8; \
      } \
      mbar_wait(bar_done + (31 - (SKEW)) * 8, par);        \
      wgmma_wait<0>(); \
      ACC_FENCE(S1, 96); \
      REL(bar_done + 31 * 8); \
      PROF(13); }
#define FOLD(tile, rd) { \
          LANE_CONSTS(); \
          float d[32]; \
          ACC_DEF(d, 32); \
          mbar_wait(bar_phi, 0); \
          wgmma_fence(); \
          _Pragma("unroll") for (int i = 0; i < 2; i++) { \
            const uint64_t da = make_desc((tile) + wg * 8192 + i * 64, 16, 1024); \
            const uint64_t db = make_desc(sbase + OFF_PHI + wg * 4096 + i * 2048, 16, 512) ^ (3ull << 62); \
            wgmma_n32<0>(d + i * 16, da, db); wgmma_n32<1>(d + i * 16, da + 2, db + 64); \
          } \
          wgmma_commit(); \
          PUMP0(); \
          ACC_FENCE(d, 32); \
          bar_wg(wg); \
          _Pragma("unroll") for (int i = 0; i < 4; i++) { \
            const float* x = d + (i & 1) * 8 + (i >> 1) * 2; \
            if (rd) sts128((tile) + wg * 8192 + ((warp & 3) * 16 + (i >> 1) * 8 + g) * 128 + (((2 * t + (i & 1)) ^ g) << 4), \
                           pack_bf16(x[0], x[1]), pack_bf16(x[4], x[5]), pack_bf16(x[16], x[17]), pack_bf16(x[20], x[21])); \
            else stsm_x4((tile) + srowoff + ((((uint32_t)i << 5) + lhi) ^ lsw), pack_bf16(d[i * 8], d[i * 8 + 1]), pack_bf16(d[i * 8 + 2], d[i * 8 + 3]), \
                         pack_bf16(d[i * 8 + 4], d[i * 8 + 5]), pack_bf16(d[i * 8 + 6], d[i * 8 + 7])); \
          } \
          }
#define XM_ISSUE() { mbar_wait(bar_xr, par); wgmma_fence(); \
      wgmma_copy(T_, dA0 + (OFF_RA >> 4), make_desc(sbase + OFF_ID, 128, 128) ^ (1ull << 62)); }
#define COPYN(d, s, n) _Pragma("unroll") for (int i_ = 0; i_ < (n); i_++) { uint32_t c_; asm volatile("mov.b32 %0, %1;" : "=r"(c_) : "f"((s)[i_])); (d)[i_] = __uint_as_float(c_); }
#define COPY64(d, s) COPYN(d, s, 64)
#define XM_DONE() { ACC_FENCE(T_, 64); COPY64(S1, T_); ACC_FENCE(S1, 64); \
      __syncwarp(); if (elect_one()) mbar_arrive_local(bar_lx); }
#define LOAD_X() { \
      uint32_t xr[32]; \
      wgmma_wait<0>(); mbar_wait(bar_xr, par); \
      _Pragma("unroll") for (int j_ = 0; j_ < 8; j_++) \
        ldsm_x4(sbase + OFF_RA + (j_ >> 2) * SLOT + srowoff + (((j_ & 3) * 32 + lhi) ^ lsw), xr[4 * j_], xr[4 * j_ + 1], xr[4 * j_ + 2], xr[4 * j_ + 3]); \
      _Pragma("unroll") for (int i_ = 0; i_ < 32; i_++) { S1[2 * i_] = bf_lo(xr[i_]); S1[2 * i_ + 1] = bf_hi(xr[i_]); } \
      ACC_FENCE(S1, 64); }

    float S0[96], S1[96];
    if (lane == 0) epoch0 = ld_relaxed(prm.epoch);
    __syncwarp();
    uint32_t ub = bar_full;
    {
      constexpr int l = 0;
      constexpr uint32_t par = 0;
      (void)l;
      ACC_DEF(S0, 96);
      QSTEP(S0, RA_CUR, 0);
      PROF(0);
      SCHED_FENCE();
      cluster_wait();
      ub += 8;
#pragma unroll 1
      for (int i = 1; i < 5; i++) {
        QSTEP(S0, dA0 + (OFF_RA >> 4) + i * (SLOT >> 4), 1);
        QREL();
      }
    }
    const unsigned epoch = __shfl_sync(0xffffffffu, epoch0, 0), ep1 = epoch + 1;
#pragma unroll 1
    for (int l = 0;; l++) {
      const uint32_t par = l & 1;
      PROF(1);
      {
        LANE_CONSTS();
        uint32_t ta[4];
#pragma unroll
        for (int j = 0; j < 4; j++) ta[j] = pK + srowoff + ((((uint32_t)j << 5) + lhi) ^ lsw);
        float p0, p1, a0 = 0.f, a1 = 0.f, q0 = 0.f, q1 = 0.f;
#define STATS(j0, j1) _Pragma("unroll") for (int j = (j0); j < (j1); j++) { \
          uint32_t x[4]; \
          ldsm_x4(ta[j & 3] + (j >> 2) * SLOT, x[0], x[1], x[2], x[3]); \
          if (j == 0) { p0 = __shfl_sync(0xffffffffu, bf_lo(x[0]), lane & 28); p1 = __shfl_sync(0xffffffffu, bf_lo(x[1]), lane & 28); } \
          _Pragma("unroll") for (int i = 0; i < 4; i += 2) { \
            const float d0 = bf_lo(x[i]) - p0, d1 = bf_hi(x[i]) - p0, d2 = bf_lo(x[i + 1]) - p1, d3 = bf_hi(x[i + 1]) - p1; \
            a0 += d0 + d1; a1 += d2 + d3; \
            q0 = fmaf(d1, d1, fmaf(d0, d0, q0)); q1 = fmaf(d3, d3, fmaf(d2, d2, q1)); } } \
          asm volatile("" : "+f"(a0), "+f"(a1), "+f"(q0), "+f"(q1), "+f"(p0), "+f"(p1)); SCHED_FENCE()
        if (SB0) { STATS(0, SB0); }
        bar_wg(wg);
        QSTEP(S0, dA0 + ((OFF_S + SLOT) >> 4), 1);
        QREL();
        SCHED_FENCE();
        STATS(SB0, SB1);
        ACC_DEF(S1, 96);
        QSTEP(S1, dA0 + (OFF_S >> 4), 0);
        QREL();
        SCHED_FENCE();
        STATS(SB1, SB2);
        QSTEP(S1, dA0 + ((OFF_S + SLOT) >> 4), 1);
        QREL();
        SCHED_FENCE();
        STATS(SB2, 8);
#pragma unroll
        for (int o = 1; o <= 2; o <<= 1) {
          a0 += __shfl_xor_sync(0xffffffffu, a0, o); a1 += __shfl_xor_sync(0xffffffffu, a1, o);
          q0 += __shfl_xor_sync(0xffffffffu, q0, o); q1 += __shfl_xor_sync(0xffffffffu, q1, o);
        }
        if (t == 1) { a0 = a1; q0 = q1; p0 = p1; }
        if (t < 2) st_b64(g_stats + (size_t)(mm * 128 + r0 + g + t * 8) * 8 + jj, __float_as_uint(fmaf(a0, 1.f / 128.f, p0)),
                          (__float_as_uint(fmaxf(fmaf(a0 * (-1.f / 128.f), a0, q0), 0.f)) & ~3u) | STAT_TAG(l));
        if (l) { asm volatile("cp.async.bulk.wait_group 0;" ::: "memory"); bar_arrive<BAR_X1, 288>(); }
#pragma unroll 1
        while (ub < bar_full + 144) {
          QSTEP(S0, RA_CUR, 1);
          if (ub == bar_full + 64) PROF(2);
          QREL();
        }
      }
      LANE_CONSTS();
      mbar_wait(bar_stat, par);
      LNSTEP(S0, 0);
      wgmma_commit();
      const float rs0 = lds32f(sbase + OFF_ST + (r0 + g) * 4), rs1 = lds32f(sbase + OFF_ST + (r0 + g + 8) * 4);
      PUMP0();
      ACC_FENCE(S0, 96);
      PROF(3);
      if (!par) {
        constexpr uint32_t par = 0;
        uint32_t qa[16];
        uint32_t kf[24], vf[24];
#define DRAIN_A(ACC, hp, PMP) { \
          LANE_CONSTS(); \
          FRAG(kf, ACC + 32, 0, (hp) * 2); \
          PMP; \
          FRAG(vf, ACC + 64, 1, (hp) * 2 + 1); \
          _Pragma("unroll") for (int i_ = 0; i_ < 16; i_++) qa[i_] = pack_bf16(ACC[2 * i_], ACC[2 * i_ + 1]); \
          PINU(qa, 16); }
        DRAIN_A(S0, 0, PUMP0());
        if (l == 0 && NLAYERS > 1) {
#pragma unroll 1
          for (int rd = 1; rd >= 0; rd--) {
            FOLD(sbase + (12 - rd) * SLOT, rd);
            asm volatile("bar.arrive %0, 288;" :: "r"(BAR_WF + 1 - rd) : "memory");
          }
        }
        PUMPS(FPUMP);
#pragma unroll 1
        for (int h = 0; h < 2; h++) {
          PROFH(4, 16);
          LANE_CONSTS();
          FRAG_PUT(kf + 16, 0); FRAG_PUT(vf + 16, 1);
          STG_ARRIVE();
          if (h) { PROF(8); LOAD_X(); PROF(9); WSTEP(); if (elect_one()) mbar_arrive_local(bar_lx);   PROF(10); } else PUMPS(HPUMP2);
          const bool gt0 = 2 * t > g, gt1 = 2 * t >= g;
          uint32_t msk[2] = {(gt0 ? 0xFFFFu : 0u) | (gt1 ? 0xFFFF0000u : 0u), g == 2 * t ? 0x10001u : 0u};
          PINU(msk, 2);
          TILE_CONSTS(sbase, false, 0);
          (void)pm0; (void)pbit;
          if (h) PROF(12);
          STG_WAIT();
          if (h) PROF(14);
          if (warp < 2) mbar_wait(bar_halo, h);
          if (h) PROF(15);
          if (h == 0) mbar_wait(ub, par);
          FRAG_GET(kf, 0);
          PROFH(5, 17);
          float s[2][3][4];
#pragma unroll
          for (int ks = 0; ks < 2; ks++)
#pragma unroll
            for (int i = 0; i < 6; i++) {
              const int hh = i & 1, jb = 2 - (i >> 1);
              const uint32_t* b = kf + jb * 8 + hh * 4 + ks * 2;
              if (ks) mma_bf16(s[hh][jb], qa[hh * 8 + 4], qa[hh * 8 + 5], qa[hh * 8 + 6], qa[hh * 8 + 7], b[0], b[1]);
              else mma_bf16_z(s[hh][jb], qa[hh * 8], qa[hh * 8 + 1], qa[hh * 8 + 2], qa[hh * 8 + 3], b[0], b[1]);
            }
          if (h == 0) PUMPN()
          PROFH(6, 18);
          float va[2][2], vb[2][2], mx[2][2];
#pragma unroll
          for (int hh = 0; hh < 2; hh++) {
            va[hh][0] = gt0 ? s[hh][0][0] : s[hh][1][0];
            vb[hh][0] = gt1 ? s[hh][0][1] : s[hh][1][1];
            va[hh][1] = gt0 ? s[hh][1][2] : s[hh][2][2];
            vb[hh][1] = gt1 ? s[hh][1][3] : s[hh][2][3];
          }
          if (warp < 2 && mm == 0) {
#pragma unroll
            for (int hh = 0; hh < 2; hh++) { if (gt0) va[hh][0] = -INFINITY; if (gt1) vb[hh][0] = -INFINITY; }
          }
#pragma unroll
          for (int i = 0; i < 4; i++) mx[i >> 1][i & 1] = fmaxf(va[i >> 1][i & 1], vb[i >> 1][i & 1]);
#pragma unroll
          for (int o = 1; o <= 2; o <<= 1)
#pragma unroll
            for (int i = 0; i < 4; i++) mx[i >> 1][i & 1] = fmaxf(mx[i >> 1][i & 1], __shfl_xor_sync(0xffffffffu, mx[i >> 1][i & 1], o));
          const float sc0 = rs0 * (0.17677669529663687f * LOG2E), sc1 = rs1 * (0.17677669529663687f * LOG2E);
#pragma unroll
          for (int i = 0; i < 4; i++) {
            const float sc = (i & 1) ? sc1 : sc0, m = mx[i >> 1][i & 1];
            va[i >> 1][i & 1] = ex2((va[i >> 1][i & 1] - m) * sc); vb[i >> 1][i & 1] = ex2((vb[i >> 1][i & 1] - m) * sc);
            mx[i >> 1][i & 1] = va[i >> 1][i & 1] + vb[i >> 1][i & 1];
          }
          if (h == 0) { PIN(&va[0][0], 4); PIN(&vb[0][0], 4); PIN(&mx[0][0], 4); PUMP1(); }
          if (h) PROF(20);
          if (warp < 2) mbar_wait(bar_halo + 8, h);
          if (h) PROF(21);
          if (h == 0) mbar_wait(ub, par);
          FRAG_GET(vf, 1);
#pragma unroll
          for (int o = 1; o <= 2; o <<= 1)
#pragma unroll
            for (int i = 0; i < 4; i++) mx[i >> 1][i & 1] += __shfl_xor_sync(0xffffffffu, mx[i >> 1][i & 1], o);
          float o[8][4];
          uint32_t pa[4][2];
#pragma unroll
          for (int i = 0; i < 4; i++) {
            const float iv = rcp_fast(mx[i >> 1][i & 1]);
            const uint32_t w = pack_bf16(va[i >> 1][i & 1] * iv, vb[i >> 1][i & 1] * iv);
            pa[i][0] = w & msk[0]; pa[i][1] = w & ~msk[0];
          }
          PROFH(7, 19);
#pragma unroll
          for (int i = 7; i >= 0; i--) {
            const uint32_t* a = vf + (i >> 2) * 8 + (i & 3) * 2;
            mma_bf16_z(o[i], a[0], a[1], a[8], a[9], pa[(i & 2) + (i >> 2)][0], pa[(i & 2) + (i >> 2)][1]);
          }
          if (h == 0) PUMPN() else mbar_wait(bar_done + 30 * 8, par);
          if (NLAYERS > 1 && l + h == 0) mbar_wait(bar_phi + 8, 0);
          if (h) PROF(22);
          {
            const uint32_t pm0 = msk[1], pbit = O_BIT(l) * 0x10001u;
#pragma unroll
            for (int i = 0; i < 4; i++)
              stsm_x4_t(ta[i] + (h ? 3 : 12) * SLOT, PBIT(pack_bf16(o[i][0], o[i][1])), PBIT(pack_bf16(o[i + 4][0], o[i + 4][1])),
                        pack_bf16(o[i][2], o[i][3]), pack_bf16(o[i + 4][2], o[i + 4][3]));
          }
          WARP_STORE(&tm_os, sbase + (h ? 3 : 12) * SLOT, jj * 128 + h * 64, mm * 128);
          PROFH(11, 23);
          if (h) break;
          REST_P1(ASKEW);
          asm volatile("cp.async.bulk.wait_group.read 0;" ::: "memory");
          DRAIN_A(S1, 1, {});
        }
      } else {
        constexpr uint32_t par = 1;
        float st[32];
        const float c0 = rs0 * LOG2E, c1 = rs1 * LOG2E;
        { V_ADDR(pV, 0); STAGE_V(S0 + 64); }
        if (warp < 2) sts128(sbase + OFF_ONES + warp * 512 + lane * 16, 0x3F803F80u, 0x3F803F80u, 0x3F803F80u, 0x3F803F80u);
        scale32(st, S0, c0, c1);
        PIN(st, 32);
#define PHI_PIECE(c) { \
          e_[2 * (c)] = ex2(st[2 * (c)]); e_[2 * (c) + 1] = ex2(st[2 * (c) + 1]); \
          _Pragma("unroll") for (int k_ = 4 * (c); k_ < 4 * (c) + 4; k_++) m_[(c) >> 1] = (k_ & 7) ? fmaf(st[k_], st[k_], m_[(c) >> 1]) : st[k_] * st[k_]; \
          asm volatile("" : "+f"(e_[2 * (c)]), "+f"(e_[2 * (c) + 1]), "+f"(m_[(c) >> 1])); SCHED_FENCE(); }
#define PHI_FIN() { \
          big = __any_sync(0xffffffffu, !(fmaxf(fmaxf(m_[0], m_[1]), fmaxf(m_[2], m_[3])) < BIGLIM)); \
          if (__builtin_expect(big, 0)) { COPYN(e_, st, 16); } \
          _Pragma("unroll") for (int k_ = 0; k_ < 16; k_++) st[k_] = e_[k_]; \
          PIN(st, 16); }
#define KV_MMA(vs, IL) { \
          const uint32_t dp = dA0 + 12 * 1024 - wg * 2560, dv = dA0 + (vs) * 1024 + ((OFF_ONES - (vs) * SLOT - 16) << 12) - wg * (512 << 16); \
          STG_WAIT(); \
          fence_proxy_async_smem(); \
          wgmma_fence(); \
          _Pragma("unroll") for (int ks = 0; ks < 8; ks++) { \
            const uint64_t a = DESC(dp + ks * 128, 0x40000040), b = DESC(dv + ks * (64 - (64 << 16)), 0x80000020); \
            if ((IL) && ks) wgmma_fence(); \
            if (ks == 0) wgmma_n40<0, 1>(kv, a, b); else wgmma_n40<1, 1>(kv, a, b); \
            if (ks == 7) wgmma_commit(); \
            if (IL) PHI_PIECE(ks); } }
#define KV_RED1(i) if (h) red_v4(g_kv[l >> 1] + (jj * 4) * KVH + warp * 768 + lane * 4 + (i) * 128, S0[32 + (i) * 3], S0[33 + (i) * 3], S0[34 + (i) * 3], 1.f)
#define KV_REDS(n) { _Pragma("unroll") for (int i_ = 0; i_ < 6; i_++) if (((RPACE >> (4 * i_)) & 15) == (n)) KV_RED1(i_); }
#define KV_SEND(kp) { \
          float sd[9]; \
          _Pragma("unroll") for (int i = 0; i < 8; i++) { (kp)[i] = kv[i]; sd[i] = kv[8 + i]; } \
          (kp)[8] = rank ? kv[18] : kv[16]; sd[8] = rank ? kv[16] : kv[18]; \
          const uint32_t ra = sbase + peer + (warp * 32 + lane) * 4, rb = bar_kx + peer; \
          if (elect_one()) mbar_expect_tx(bar_kx, 1152); \
          _Pragma("unroll") for (int i = 0; i < 2; i++) \
            asm volatile("st.async.weak.shared::cluster.mbarrier::complete_tx::bytes.v4.f32 [%0], {%1, %2, %3, %4}, [%5];" \
                         :: "r"(ra + (warp * 32 + lane) * 12 + OFF_PHI + i * 4096), "f"(sd[4 * i]), "f"(sd[4 * i + 1]), "f"(sd[4 * i + 2]), "f"(sd[4 * i + 3]), "r"(rb) : "memory"); \
          asm volatile("st.async.weak.shared::cluster.mbarrier::complete_tx::bytes.f32 [%0], %1, [%2];" :: "r"(ra + OFF_LNB), "f"(sd[8]), "r"(rb) : "memory"); }
#define KV_RECV(kp, hp) { \
          float r_[9]; \
          float* kvg = g_kv[l >> 1] + (jj * 4 + (hp) * 2) * KVH + warp * 768 + rank * 384 + lane * 4; \
          mbar_wait(bar_kx, l >> 1); \
          _Pragma("unroll") for (int i = 0; i < 2; i++) \
            asm volatile("ld.shared.v4.f32 {%0, %1, %2, %3}, [%4];" : "=f"(r_[4 * i]), "=f"(r_[4 * i + 1]), "=f"(r_[4 * i + 2]), "=f"(r_[4 * i + 3]) \
                         : "r"(sbase + OFF_PHI + i * 4096 + (warp * 32 + lane) * 16) : "memory"); \
          r_[8] = lds32f(sbase + OFF_LNB + (warp * 32 + lane) * 4); \
          _Pragma("unroll") for (int i = 0; i < 3; i++) red_v4(kvg + i * 128, (kp)[3 * i] + r_[3 * i], (kp)[3 * i + 1] + r_[3 * i + 1], (kp)[3 * i + 2] + r_[3 * i + 2], 2.f); }
#define KV_LOAD(hp) { \
          const uint4* kvg = reinterpret_cast<const uint4*>(g_kv[l >> 1] + (jj * 4 + (hp) * 2) * KVH) + warp * 192 + lane; \
          _Pragma("unroll") for (int i = 0; i < 6; i++) v[i] = ld_b128(kvg + i * 32); }
#define KVV(i) __uint_as_float((i) % 3 == 0 ? v[(i) / 3].x : ((i) % 3 == 1 ? v[(i) / 3].y : v[(i) / 3].z))
#define KV_TILE(hp) { \
          _Pragma("unroll 1") for (int it = 0; it < (1 << 16); it++) { \
            if (__all_sync(0xffffffffu, (v[0].w & v[1].w & v[2].w & v[3].w & v[4].w & v[5].w) == 0x41800000u)) break; \
            RETRY_COUNT(); \
            KV_LOAD(hp); \
          } \
          if (hp) PROF(26); else PROF(25); \
          const uint32_t e = lane & 7, jt = ((lane >> 1) & 4) + (e >> 1); \
          const uint32_t row = ((((warp >> 1) ^ wg) & 1) << 5) + ((jt & 1) << 4) + ((warp & 1) << 3) + (jt & 6) + (e & 1); \
          const uint32_t kd = pV + wg * 8192 + row * 128, ksw = (row & 7) << 4; \
          _Pragma("unroll") for (int i = 0; i < 2; i++) \
            stsm_x4(kd + ((i * 32 + lhi) ^ ksw), pack_bf16(KVV(i * 9), KVV(i * 9 + 1)), pack_bf16(KVV(i * 9 + 2), KVV(i * 9 + 3)), \
                    pack_bf16(KVV(i * 9 + 4), KVV(i * 9 + 5)), pack_bf16(KVV(i * 9 + 6), KVV(i * 9 + 7))); \
          stsm_x4(kd + ((64u + lhi) ^ ksw), pack_bf16(KVV(8), 1.f), pack_bf16(KVV(17), 1.f), 0u, 0u); }
#pragma unroll 1
        for (int h = 0; h < 2; h++) {
          PROFH(4, 6);
          PUMP0();
          LANE_CONSTS();
          const uint32_t dsw = (uint32_t)(g ^ (2 * t)) << 4, dst = ((t & 2) ? pK : sbase + 12 * SLOT) + (r0 + g) * 128;
          float e[16], f[16];
          KV_REDS(1);
          float sa = exps16_<0>(e, st);
          exps16_fix<0>(e, st, sa);
          asm volatile("" : "+f"(sa)); PIN(e, 16); PUMP0();
          if (h) STG_WAIT();
          KV_REDS(2);
          store16(e, sa, dst, dsw, 4);
          float sb = exps16_<1>(f, st);
          exps16_fix<1>(f, st, sb);
          asm volatile("" : "+f"(sb)); PIN(f, 16); PUMP0();
          KV_REDS(3);
          store16(f, sb, dst, dsw, 0);
          float sc = exps16_<0>(e, st + 2);
          exps16_fix<0>(e, st + 2, sc);
          asm volatile("" : "+f"(sc)); PIN(e, 16); PUMP0();
          KV_REDS(4);
          store16(e, sc, dst + 1024, dsw, 4);
          float sd = exps16_<1>(f, st + 2);
          exps16_fix<1>(f, st + 2, sd);
          asm volatile("" : "+f"(sd)); PIN(f, 16); PUMP0();
          store16(f, sd, dst + 1024, dsw, 0);
          PROFH(5, 7);
          if (h) break;
          {
            float kv[20];
            ACC_DEF(kv, 20);
            STG_ARRIVE();
            float e_[16], m_[4];
            KV_MMA(11, 0);
            PUMP0();
            ACC_FENCE(kv, 20);
            STG_ARRIVE();
            scale32(st, S0 + 32, c0, c1);
            PIN(st, 32);
            {
              COPYN(S0 + 32, kv, 8); COPYN(S0 + 40, kv + 16, 1); COPYN(S0 + 41, kv + 8, 8); COPYN(S0 + 49, kv + 18, 1);
              const int h = 1;
              KV_REDS(0);
            }
          }
        }
        bool big;
        uint4 v[6];
        {
          float kv[20];
          { LANE_CONSTS(); KV_LOAD(0); }
          mbar_wait(bar_stat2, par);
          ub = bar_full + 240;
          LNSTEP(S1, 1);
          PUMP1();
          if (wg == 0) bar_sync<BAR_SKEW, 256>();
          QSTEP(S1, RA_CUR, 1);
          if (wg == 1) bar_arrive<BAR_SKEW, 256>();
          QREL();
          { LANE_CONSTS(); KV_TILE(0); }
          LANE_CONSTS();
          V_ADDR(sbase + 3 * SLOT, rank * 32);
          PINU(va_, 2);
          mbar_wait(bar_done + 30 * 8, par);
          wgmma_wait<0>();
          ACC_FENCE(S1, 96);
          PROF(13);
          STAGE_V(S1 + 64);
          STG_ARRIVE();
          REL(bar_done + 31 * 8);
          scale32(st, S1, c0, c1);
          PIN(st, 32);
          PROF(16);
          ACC_DEF(kv, 20);
          float e_[16], m_[4];
          KV_MMA(3, 1);
          SCHED_FENCE();
          PROF(14);
          PHI_FIN();
          SCHED_FENCE();
          PROF(15);
          wgmma_wait<0>();
          ACC_FENCE(kv, 20);
          PROF(12);
          { float kp[9]; KV_SEND(kp); _Pragma("unroll") for (int i = 0; i < 3; i++) v[i] = make_uint4(__float_as_uint(kp[3 * i]), __float_as_uint(kp[3 * i + 1]), __float_as_uint(kp[3 * i + 2]), 0u); }
#define VDEF(i0) _Pragma("unroll") for (int i = (i0); i < 6; i++) asm volatile("" : "=r"(v[i].x), "=r"(v[i].y), "=r"(v[i].z), "=r"(v[i].w))
          VDEF(3);
          PROF(17);
        }
#pragma unroll 1
        for (int h = 0; h < 2; h++) {
          const uint32_t pO = sbase + (h ? 3 : 8) * SLOT;
          LANE_CONSTS();
          uint32_t fq[32];
          if (h) { KV_LOAD(1); phiq_a(st, big); PIN(st, 16); PROF(31); }
          PROFH(18, 32);
          SCHED_FENCE();
          phiq_b<1>(fq, st, big); PINU(fq, 16); PIN(st + 16, 16);
          SCHED_FENCE();
          PROFH(8, 9);
          if (h) {
            asm volatile("cp.async.bulk.wait_group.read 0;" ::: "memory");
            mbar_wait(bar_lx, par);
            PROF(30);
            KV_TILE(1);
            STG_ARRIVE();
          }
          SCHED_FENCE();
          if (h == 0) {
            float kp[9];
#pragma unroll
            for (int i = 0; i < 9; i++) kp[i] = KVV(i);
            KV_RECV(kp, 1);
            SCHED_FENCE();
          }
          phiq_b<0>(fq + 16, st + 16, big); PINU(fq + 16, 16);
          PROFH(10, 21);
          if (h) { STG_WAIT(); fence_proxy_async_smem(); }
          wgmma_wait<0>();
          ACC_FENCE(S1, 64);
          PROFH(19, 33);
          float o[4][20];
#define O_MMA(hh) { \
            const uint64_t db = make_desc(pV + (hh) * 8192, 16, 1024); \
            ACC_DEF(o[(hh) * 2], 20); ACC_DEF(o[(hh) * 2 + 1], 20); \
            wgmma_fence(); \
            wgmma_n40_rs<0>(o[(hh) * 2], fq + (hh) * 16, db + 256); wgmma_n40_rs<0>(o[(hh) * 2 + 1], fq + (hh) * 16 + 8, db); \
            wgmma_n40_rs<1>(o[(hh) * 2], fq + (hh) * 16 + 4, db + 384); wgmma_n40_rs<1>(o[(hh) * 2 + 1], fq + (hh) * 16 + 12, db + 128); \
            wgmma_commit(); }
          O_MMA(0);
          SCHED_FENCE();
          PMASKS(true, O_BIT(l));
#pragma unroll
          for (int hh = 0; hh < 2; hh++) {
            wgmma_wait<0>();
            ACC_FENCE(o[hh * 2], 20); ACC_FENCE(o[hh * 2 + 1], 20);
            if (!hh) { O_MMA(1); SCHED_FENCE(); }
            if (hh) PROFH(22, 24);
            const float* x = o[hh * 2];
            const float* y = o[hh * 2 + 1];
            const float sx0 = x[17] * 0x1p-40f, sy0 = y[17] * 0x1p-40f, sx1 = x[19] * 0x1p-40f, sy1 = y[19] * 0x1p-40f;
            const float i0 = rcp_fast(fmaf(fmaf(x[17], 1e-6f, x[16]), sy0, y[16] * sx0)), i1 = rcp_fast(fmaf(fmaf(x[19], 1e-6f, x[18]), sy1, y[18] * sx1));
            const float ax0 = sy0 * i0, ay0 = sx0 * i0, ax1 = sy1 * i1, ay1 = sx1 * i1;
#pragma unroll
            for (int dp = 0; dp < 2; dp++)
              stsm_x4(pO + srowoff + ((hh * 64 + dp * 32 + lhi) ^ lsw),
                      PBIT(pack_bf16(fmaf(x[dp * 8], ax0, y[dp * 8] * ay0), fmaf(x[dp * 8 + 1], ax0, y[dp * 8 + 1] * ay0))),
                      PBIT(pack_bf16(fmaf(x[dp * 8 + 2], ax1, y[dp * 8 + 2] * ay1), fmaf(x[dp * 8 + 3], ax1, y[dp * 8 + 3] * ay1))),
                      (pack_bf16(fmaf(x[dp * 8 + 4], ax0, y[dp * 8 + 4] * ay0), fmaf(x[dp * 8 + 5], ax0, y[dp * 8 + 5] * ay0))),
                      (pack_bf16(fmaf(x[dp * 8 + 6], ax1, y[dp * 8 + 6] * ay1), fmaf(x[dp * 8 + 7], ax1, y[dp * 8 + 7] * ay1))));
          }
          WARP_STORE(&tm_os, pO, jj * 128 + h * 64, mm * 128);
          PROFH(20, 34);
          if (h) break;
          float T_[64];
          scale32(st, S1 + 32, c0, c1);
          PIN(st, 32);
          ACC_DEF(T_, 64);
          XM_ISSUE(); wgmma_commit();
          SCHED_FENCE();
          big = any_big(st);
          SCHED_FENCE();
          PROF(27);
          wgmma_wait<0>(); XM_DONE();
          PROF(28);
          bar_wg(wg);
          WSTEP();
          SCHED_FENCE();
          VDEF(0);
          PROF(29);
        }
      }
      __syncwarp();
      if (elect_one()) mbar_arrive_local(bar_epi);
      bar_wg(wg);
#pragma unroll 1
      while (ub < bar_full + 384) {
        if (FSK && l == NLAYERS - 1 && wg == 0 && ub == bar_full + 384 - 8 * FSK) bar_sync<BAR_SKEW, 256>();
        if (FSK && l == NLAYERS - 1 && wg == 1 && ub == bar_full + 376) { mbar_wait(ub, par); bar_arrive<BAR_SKEW, 256>(); }
        WSTEP();
        if (ub == bar_full + 8 * 41) { asm volatile("cp.async.bulk.wait_group.read 0;" ::: "memory"); PROF(35); }
        if (ub == bar_full + 8 * 42) PROF(36);
      }
      {
        float Wb[32];
        LANE_CONSTS();
        TILE_CONSTS(pK, l < NLAYERS - 1, X_BIT(l));
        if (l < NLAYERS - 1) mbar_wait(bar_full, par ^ 1);
        wgmma_wait<0>();
        ACC_FENCE(S1, 64);
        COPYN(Wb, S1 + 32, 32);
        PROF(37);
        uint32_t xa[16];
#pragma unroll
        for (int i = 0; i < 16; i++) { const uint32_t w = pack_bf16(S1[2 * i], S1[2 * i + 1]); xa[i] = (i & 2) ? w : PBIT(w); }
        PINU(xa, 16);
#define XA_OUT() _Pragma("unroll") for (int j = 0; j < 4; j++) stsm_x4(ta[j], xa[4 * j], xa[4 * j + 1], xa[4 * j + 2], xa[4 * j + 3])
        if (l == NLAYERS - 1) {
          XA_OUT();
          const uint32_t src = pK + (r0 + (lane >> 3)) * 128 + (((lane ^ (lane >> 3)) & 7) << 4);
          uint4* dst = reinterpret_cast<uint4*>(prm.out + (size_t)(mm * 128 + (warp >> 1) * 32 + (warp & 1) + (lane >> 3) * 2) * D_MODEL + jj * 128) + (lane & 7);
#pragma unroll
          for (int pc = 0; pc < 2; pc++) {
            if (pc) { PMASKS(false, 0); X_OUT(1, Wb); }
            __syncwarp();
            uint4 y[4];
#pragma unroll
            for (int i = 0; i < 4; i++)
              asm volatile("ld.shared.v4.u32 {%0, %1, %2, %3}, [%4];" : "=r"(y[i].x), "=r"(y[i].y), "=r"(y[i].z), "=r"(y[i].w) : "r"((src + pc * SLOT + i * 512) ^ ((i & 1) << 6)) : "memory");
#pragma unroll
            for (int i = 0; i < 4; i++) dst[pc * 8 + i * 1024] = y[i];
            if (pc) PROF(39); else PROF(38);
          }
          break;
        }
        PROF(38);
        XA_OUT();
        ACC_DEF(S0, 96);
        wgmma_fence();
        wgmma_n192_rs<0>(S0, xa, dB0);
#pragma unroll
        for (int k = 1; k < RSK; k++) wgmma_n192_rs<1>(S0, xa + 4 * k, dB0 + 128 * k);
        wgmma_commit();
        WARP_STORE(&tm_os, pK, jj * 128, mm * 128 + S_LEN);
        if (RSK < 4) {
          wgmma_fence();
#pragma unroll
          for (int k = RSK; k < 4; k++) wgmma_n192_rs<1>(S0, xa + 4 * k, dB0 + 128 * k);
          wgmma_commit();
        }
        { const int ln_ = l + 1, l = ln_; const uint32_t ub = bar_full; (void)l; (void)ub; PROFS(); }
        REL(bar_done + 47 * 8);
        ub = bar_full + 8;
        PROF(39);
        { PMASKS(false, 0); X_OUT(1, Wb); }
        fence_proxy_async_smem();
      }
    }
    cluster_sync();
    if (threadIdx.x == 0) PROFT(487);
  }
}

typedef CUresult (*PFN_encode)(CUtensorMap*, CUtensorMapDataType, cuuint32_t, void*, const cuuint64_t*, const cuuint64_t*,
                               const cuuint32_t*, const cuuint32_t*, CUtensorMapInterleave, CUtensorMapSwizzle,
                               CUtensorMapL2promotion, CUtensorMapFloatOOBfill);

CUtensorMap make_map(PFN_encode enc, const void* ptr, uint64_t inner, uint64_t outer, uint32_t box_inner, uint32_t box_outer,
                     CUtensorMapSwizzle swz = CU_TENSOR_MAP_SWIZZLE_128B, int promo = CU_TENSOR_MAP_L2_PROMOTION_L2_256B) {
  CUtensorMap m;
  cuuint64_t dims[2] = {inner, outer};
  cuuint64_t strides[1] = {inner * 2};
  cuuint32_t box[2] = {box_inner, box_outer};
  cuuint32_t es[2] = {1, 1};
  enc(&m, CU_TENSOR_MAP_DATA_TYPE_BFLOAT16, 2, const_cast<void*>(ptr), dims, strides, box, es, CU_TENSOR_MAP_INTERLEAVE_NONE,
      swz, (CUtensorMapL2promotion)promo, CU_TENSOR_MAP_FLOAT_OOB_FILL_NONE);
  return m;
}

CUtensorMap make_tile_map(PFN_encode enc, const void* ptr, uint64_t rows, bool by_parity, int promo) {
  CUtensorMap m;
  cuuint64_t dims[4] = {D_MODEL, 16, 2, rows / 32};
  cuuint64_t strides[3] = {by_parity ? 4096u : 2048u, by_parity ? 2048u : 32768u, 65536};
  cuuint32_t box[4] = {64, 16, 2, 4};
  cuuint32_t es[4] = {1, 1, 1, 1};
  enc(&m, CU_TENSOR_MAP_DATA_TYPE_BFLOAT16, 4, const_cast<void*>(ptr), dims, strides, box, es, CU_TENSOR_MAP_INTERLEAVE_NONE,
      CU_TENSOR_MAP_SWIZZLE_128B, (CUtensorMapL2promotion)promo, CU_TENSOR_MAP_FLOAT_OOB_FILL_NONE);
  return m;
}

}

extern "C" void kernel_launch(void* const* d_in, const int* in_sizes, int n_in, void* d_out, int out_size) {
  (void)in_sizes; (void)n_in; (void)out_size;
  static PFN_encode enc = nullptr;
  if (!enc) {
    void* fn = nullptr;
    cudaDriverEntryPointQueryResult qr;
    cudaGetDriverEntryPoint("cuTensorMapEncodeTiled", &fn, cudaEnableDefault, &qr);
    enc = (PFN_encode)fn;
    cudaFuncSetAttribute(mega_kernel, cudaFuncAttributeMaxDynamicSharedMemorySize, SMEM_BYTES);
  }
  Params prm;
  prm.wA_o = (const __nv_bfloat16*)d_in[2];
  prm.wB_qkv = (const __nv_bfloat16*)d_in[4];
  prm.wB_o = (const __nv_bfloat16*)d_in[6];
  prm.out = (__nv_bfloat16*)d_out;
  void *obuf = nullptr, *wf = nullptr, *fl = nullptr;
  cudaGetSymbolAddress(&fl, g_flags);
  prm.epoch = &static_cast<Flags*>(fl)->epoch.v;
  cudaGetSymbolAddress(&obuf, g_obuf);
  cudaGetSymbolAddress(&wf, g_wfold);
  CUtensorMap tm_x0 = make_tile_map(enc, d_in[0], S_LEN, true, XPROMO);
  CUtensorMap tm_os = make_map(enc, obuf, D_MODEL, 2 * S_LEN, 64, 16);
  CUtensorMap tm_o = make_tile_map(enc, obuf, 2 * S_LEN, false, OPROMO);
  CUtensorMap tm_wf = make_map(enc, wf, 2048, D_MODEL, 64, 32);
  CUtensorMap tm_wqA = make_map(enc, d_in[1], 3 * D_MODEL, D_MODEL, 64, 32, CU_TENSOR_MAP_SWIZZLE_128B, WPROMO);
  CUtensorMap tm_wqB = make_map(enc, prm.wB_qkv, 3 * D_MODEL, D_MODEL, 64, 32);
  CUtensorMap tm_woA = make_map(enc, prm.wA_o, D_MODEL, D_MODEL, 64, 64);
  CUtensorMap tm_woB = make_map(enc, prm.wB_o, D_MODEL, D_MODEL, 64, 64);
  CUtensorMap tm_phi = make_map(enc, d_in[5], 32, 1024, 32, 128, CU_TENSOR_MAP_SWIZZLE_64B);
  mega_kernel<<<NMAIN + NAUX, 384, SMEM_BYTES>>>(prm, tm_x0, tm_os, tm_o, tm_wf, tm_wqA, tm_wqB, tm_woA, tm_woB, tm_phi);
}
```
